```python
import torch

def _softmax(x, axis=-1):
    return torch.softmax(x, dim=axis)

def _gelu(x):
    return torch.nn.functional.gelu(x, approximate='tanh')

def _silu(x):
    return torch.nn.functional.silu(x)

def _sigmoid(x):
    return torch.sigmoid(x)

def _layernorm(x, axis=-1, eps=1e-05):
    m = x.mean(dim=axis, keepdim=True)
    v = x.var(dim=axis, keepdim=True, unbiased=False)
    return (x - m) / torch.sqrt(v + eps)

def _scatter_add(tgt, idx, src, axis=0):
    return tgt.clone().index_add_(axis, idx, src)

def _segment_sum(src, seg, n):
    out = torch.zeros((n,) + src.shape[1:], dtype=src.dtype)
    return out.index_add_(0, seg, src)

def _pad(x, pw):
    flat = tuple((v for pair in reversed(pw) for v in pair))
    return torch.nn.functional.pad(x, flat)
kernel_name = 'adaLN_cond__sliding_block__glu_gated_reglu__prompt'

def setup_inputs():

    _w = lambda a: (lambda t: t.to(torch.bfloat16) if t.is_floating_point() else t)(torch.as_tensor(a))

    def _A_setup():
        B, S, D = (1, 2048, 448)
        return {'x': _w((lambda *s: torch.randn(*s, dtype=torch.bfloat16) * 0.05)(B, S, D)), 'wqkv': _w((lambda *s: torch.randn(*s, dtype=torch.bfloat16) * 0.05)(D, 3 * D)), 'wo': _w((lambda *s: torch.randn(*s, dtype=torch.bfloat16) * 0.05)(D, D))}
    _A_in = _A_setup()

    def _B_setup():
        B, S, D, F = (1, 2048, 448, 1792)
        return {'x': _w((lambda *s: torch.randn(*s, dtype=torch.bfloat16) * 0.05)(B, S, D)), 'W_gate': _w((lambda *s: torch.randn(*s, dtype=torch.bfloat16) * 0.8)(D, F) * (2.0 / D) ** 0.5), 'W_up': _w((lambda *s: torch.randn(*s, dtype=torch.bfloat16) * 0.8)(D, F) * (2.0 / D) ** 0.5), 'W_down': _w((lambda *s: torch.randn(*s, dtype=torch.bfloat16) * 0.8)(F, D) * (1.0 / F) ** 0.5)}
    _B_in = _B_setup()
    return {'A_x': _A_in['x'], 'A_wqkv': _A_in['wqkv'], 'A_wo': _A_in['wo'], 'B_x': _B_in['x'], 'B_W_gate': _B_in['W_gate'], 'B_W_up': _B_in['W_up'], 'B_W_down': _B_in['W_down'], 'c': _w((lambda *s: torch.randn(*s, dtype=torch.bfloat16) * 0.1)(1, 448) * 8.0), 'w_mod': _w((lambda *s: torch.randn(*s, dtype=torch.bfloat16) * 0.1)(448, 6 * 448) * 448 ** (-0.5) * 8.0)}

def reference(A_x, A_wqkv, A_wo, B_x, B_W_gate, B_W_up, B_W_down, c, w_mod):

    def _A_ref(x, wqkv, wo):
        B, S, D = x.shape
        H = 16
        Dh = D // H
        W = 256
        qkv = (lambda x, *d: x.permute(*d))((x @ wqkv).reshape(B, S, 3, H, Dh), 2, 0, 3, 1, 4)
        q, k, v = (qkv[0], qkv[1], qkv[2])
        scores = torch.einsum('bhqd,bhkd->bhqk', q, k) * Dh ** (-0.5)
        idx = torch.arange(S)
        mask = (idx[:, None] - idx[None, :] >= 0) & (idx[:, None] - idx[None, :] < W)
        scores = torch.where(mask[None, None], scores, -1000000000.0)
        p = _softmax(scores, axis=-1)
        o = torch.einsum('bhqk,bhkd->bhqd', p, v)
        return (lambda x, *d: x.permute(*d))(o, 0, 2, 1, 3).reshape(B, S, D) @ wo

    def _B_ref(x, W_gate, W_up, W_down):
        gate = torch.einsum('bsd,df->bsf', x, W_gate)
        up = torch.einsum('bsd,df->bsf', x, W_up)
        gate = gate * (lambda x, dt: x.to(dt))(gate > 0, gate.dtype)
        h = gate * up
        return torch.einsum('bsf,fd->bsd', h, W_down)
    x = A_x
    mod = (_silu(c) @ w_mod).reshape(c.shape[0], 6, 1, -1)
    sa, ca, ga, sb, cb, gb = (mod[:, 0].clone(), mod[:, 1].clone(), mod[:, 2].clone(), mod[:, 3].clone(), mod[:, 4].clone(), mod[:, 5].clone())
    h = _layernorm(x, axis=-1) * (1 + ca) + sa
    x = x + ga * _A_ref(h, A_wqkv, A_wo)
    h = _layernorm(x, axis=-1) * (1 + cb) + sb
    x = x + gb * _B_ref(h, B_W_gate, B_W_up, B_W_down)
    return x
```

```cpp
#include <cuda_runtime.h>
#include <cuda_bf16.h>
#include <cuda.h>
#include <stdint.h>

typedef __nv_bfloat16 bf16;

template<int TB> __device__ __forceinline__ void wgmma_ss_56(float* d, uint64_t da, uint64_t db, int sd) {
  asm volatile("{\n.reg .pred p;\nsetp.ne.b32 p, %30, 0;\n"
    "wgmma.mma_async.sync.aligned.m64n56k16.f32.bf16.bf16 {%0,%1,%2,%3,%4,%5,%6,%7,%8,%9,%10,%11,%12,%13,%14,%15,%16,%17,%18,%19,%20,%21,%22,%23,%24,%25,%26,%27}, %28, %29, p, 1, 1, 0, %31;\n}\n"
    : "+f"(d[0]),"+f"(d[1]),"+f"(d[2]),"+f"(d[3]),"+f"(d[4]),"+f"(d[5]),"+f"(d[6]),"+f"(d[7]),"+f"(d[8]),"+f"(d[9]),"+f"(d[10]),"+f"(d[11]),"+f"(d[12]),"+f"(d[13]),"+f"(d[14]),"+f"(d[15]),"+f"(d[16]),"+f"(d[17]),"+f"(d[18]),"+f"(d[19]),"+f"(d[20]),"+f"(d[21]),"+f"(d[22]),"+f"(d[23]),"+f"(d[24]),"+f"(d[25]),"+f"(d[26]),"+f"(d[27])
    : "l"(da), "l"(db), "r"(sd), "n"(TB));
}
template<int TB> __device__ __forceinline__ void wgmma_rs_56(float* d, uint32_t a0, uint32_t a1, uint32_t a2, uint32_t a3, uint64_t db, int sd) {
  asm volatile("{\n.reg .pred p;\nsetp.ne.b32 p, %33, 0;\n"
    "wgmma.mma_async.sync.aligned.m64n56k16.f32.bf16.bf16 {%0,%1,%2,%3,%4,%5,%6,%7,%8,%9,%10,%11,%12,%13,%14,%15,%16,%17,%18,%19,%20,%21,%22,%23,%24,%25,%26,%27}, {%28,%29,%30,%31}, %32, p, 1, 1, %34;\n}\n"
    : "+f"(d[0]),"+f"(d[1]),"+f"(d[2]),"+f"(d[3]),"+f"(d[4]),"+f"(d[5]),"+f"(d[6]),"+f"(d[7]),"+f"(d[8]),"+f"(d[9]),"+f"(d[10]),"+f"(d[11]),"+f"(d[12]),"+f"(d[13]),"+f"(d[14]),"+f"(d[15]),"+f"(d[16]),"+f"(d[17]),"+f"(d[18]),"+f"(d[19]),"+f"(d[20]),"+f"(d[21]),"+f"(d[22]),"+f"(d[23]),"+f"(d[24]),"+f"(d[25]),"+f"(d[26]),"+f"(d[27])
    : "r"(a0), "r"(a1), "r"(a2), "r"(a3), "l"(db), "r"(sd), "n"(TB));
}
template<int TB> __device__ __forceinline__ void wgmma_ss_160(float* d, uint64_t da, uint64_t db, int sd) {
  asm volatile("{\n.reg .pred p;\nsetp.ne.b32 p, %82, 0;\n"
    "wgmma.mma_async.sync.aligned.m64n160k16.f32.bf16.bf16 {%0,%1,%2,%3,%4,%5,%6,%7,%8,%9,%10,%11,%12,%13,%14,%15,%16,%17,%18,%19,%20,%21,%22,%23,%24,%25,%26,%27,%28,%29,%30,%31,%32,%33,%34,%35,%36,%37,%38,%39,%40,%41,%42,%43,%44,%45,%46,%47,%48,%49,%50,%51,%52,%53,%54,%55,%56,%57,%58,%59,%60,%61,%62,%63,%64,%65,%66,%67,%68,%69,%70,%71,%72,%73,%74,%75,%76,%77,%78,%79}, %80, %81, p, 1, 1, 0, %83;\n}\n"
    : "+f"(d[0]),"+f"(d[1]),"+f"(d[2]),"+f"(d[3]),"+f"(d[4]),"+f"(d[5]),"+f"(d[6]),"+f"(d[7]),"+f"(d[8]),"+f"(d[9]),"+f"(d[10]),"+f"(d[11]),"+f"(d[12]),"+f"(d[13]),"+f"(d[14]),"+f"(d[15]),"+f"(d[16]),"+f"(d[17]),"+f"(d[18]),"+f"(d[19]),"+f"(d[20]),"+f"(d[21]),"+f"(d[22]),"+f"(d[23]),"+f"(d[24]),"+f"(d[25]),"+f"(d[26]),"+f"(d[27]),"+f"(d[28]),"+f"(d[29]),"+f"(d[30]),"+f"(d[31]),"+f"(d[32]),"+f"(d[33]),"+f"(d[34]),"+f"(d[35]),"+f"(d[36]),"+f"(d[37]),"+f"(d[38]),"+f"(d[39]),"+f"(d[40]),"+f"(d[41]),"+f"(d[42]),"+f"(d[43]),"+f"(d[44]),"+f"(d[45]),"+f"(d[46]),"+f"(d[47]),"+f"(d[48]),"+f"(d[49]),"+f"(d[50]),"+f"(d[51]),"+f"(d[52]),"+f"(d[53]),"+f"(d[54]),"+f"(d[55]),"+f"(d[56]),"+f"(d[57]),"+f"(d[58]),"+f"(d[59]),"+f"(d[60]),"+f"(d[61]),"+f"(d[62]),"+f"(d[63]),"+f"(d[64]),"+f"(d[65]),"+f"(d[66]),"+f"(d[67]),"+f"(d[68]),"+f"(d[69]),"+f"(d[70]),"+f"(d[71]),"+f"(d[72]),"+f"(d[73]),"+f"(d[74]),"+f"(d[75]),"+f"(d[76]),"+f"(d[77]),"+f"(d[78]),"+f"(d[79])
    : "l"(da), "l"(db), "r"(sd), "n"(TB));
}
template<int TB> __device__ __forceinline__ void wgmma_rs_32(float* d, uint32_t a0, uint32_t a1, uint32_t a2, uint32_t a3, uint64_t db, int sd) {
  asm volatile("{\n.reg .pred p;\nsetp.ne.b32 p, %21, 0;\n"
    "wgmma.mma_async.sync.aligned.m64n32k16.f32.bf16.bf16 {%0,%1,%2,%3,%4,%5,%6,%7,%8,%9,%10,%11,%12,%13,%14,%15}, {%16,%17,%18,%19}, %20, p, 1, 1, %22;\n}\n"
    : "+f"(d[0]),"+f"(d[1]),"+f"(d[2]),"+f"(d[3]),"+f"(d[4]),"+f"(d[5]),"+f"(d[6]),"+f"(d[7]),"+f"(d[8]),"+f"(d[9]),"+f"(d[10]),"+f"(d[11]),"+f"(d[12]),"+f"(d[13]),"+f"(d[14]),"+f"(d[15])
    : "r"(a0), "r"(a1), "r"(a2), "r"(a3), "l"(db), "r"(sd), "n"(TB));
}
template<int TB> __device__ __forceinline__ void wgmma_ss_256(float* d, uint64_t da, uint64_t db, int sd) {
  asm volatile("{\n.reg .pred p;\nsetp.ne.b32 p, %130, 0;\n"
    "wgmma.mma_async.sync.aligned.m64n256k16.f32.bf16.bf16 {%0,%1,%2,%3,%4,%5,%6,%7,%8,%9,%10,%11,%12,%13,%14,%15,%16,%17,%18,%19,%20,%21,%22,%23,%24,%25,%26,%27,%28,%29,%30,%31,%32,%33,%34,%35,%36,%37,%38,%39,%40,%41,%42,%43,%44,%45,%46,%47,%48,%49,%50,%51,%52,%53,%54,%55,%56,%57,%58,%59,%60,%61,%62,%63,%64,%65,%66,%67,%68,%69,%70,%71,%72,%73,%74,%75,%76,%77,%78,%79,%80,%81,%82,%83,%84,%85,%86,%87,%88,%89,%90,%91,%92,%93,%94,%95,%96,%97,%98,%99,%100,%101,%102,%103,%104,%105,%106,%107,%108,%109,%110,%111,%112,%113,%114,%115,%116,%117,%118,%119,%120,%121,%122,%123,%124,%125,%126,%127}, %128, %129, p, 1, 1, 0, %131;\n}\n"
    : "+f"(d[0]),"+f"(d[1]),"+f"(d[2]),"+f"(d[3]),"+f"(d[4]),"+f"(d[5]),"+f"(d[6]),"+f"(d[7]),"+f"(d[8]),"+f"(d[9]),"+f"(d[10]),"+f"(d[11]),"+f"(d[12]),"+f"(d[13]),"+f"(d[14]),"+f"(d[15]),"+f"(d[16]),"+f"(d[17]),"+f"(d[18]),"+f"(d[19]),"+f"(d[20]),"+f"(d[21]),"+f"(d[22]),"+f"(d[23]),"+f"(d[24]),"+f"(d[25]),"+f"(d[26]),"+f"(d[27]),"+f"(d[28]),"+f"(d[29]),"+f"(d[30]),"+f"(d[31]),"+f"(d[32]),"+f"(d[33]),"+f"(d[34]),"+f"(d[35]),"+f"(d[36]),"+f"(d[37]),"+f"(d[38]),"+f"(d[39]),"+f"(d[40]),"+f"(d[41]),"+f"(d[42]),"+f"(d[43]),"+f"(d[44]),"+f"(d[45]),"+f"(d[46]),"+f"(d[47]),"+f"(d[48]),"+f"(d[49]),"+f"(d[50]),"+f"(d[51]),"+f"(d[52]),"+f"(d[53]),"+f"(d[54]),"+f"(d[55]),"+f"(d[56]),"+f"(d[57]),"+f"(d[58]),"+f"(d[59]),"+f"(d[60]),"+f"(d[61]),"+f"(d[62]),"+f"(d[63]),"+f"(d[64]),"+f"(d[65]),"+f"(d[66]),"+f"(d[67]),"+f"(d[68]),"+f"(d[69]),"+f"(d[70]),"+f"(d[71]),"+f"(d[72]),"+f"(d[73]),"+f"(d[74]),"+f"(d[75]),"+f"(d[76]),"+f"(d[77]),"+f"(d[78]),"+f"(d[79]),"+f"(d[80]),"+f"(d[81]),"+f"(d[82]),"+f"(d[83]),"+f"(d[84]),"+f"(d[85]),"+f"(d[86]),"+f"(d[87]),"+f"(d[88]),"+f"(d[89]),"+f"(d[90]),"+f"(d[91]),"+f"(d[92]),"+f"(d[93]),"+f"(d[94]),"+f"(d[95]),"+f"(d[96]),"+f"(d[97]),"+f"(d[98]),"+f"(d[99]),"+f"(d[100]),"+f"(d[101]),"+f"(d[102]),"+f"(d[103]),"+f"(d[104]),"+f"(d[105]),"+f"(d[106]),"+f"(d[107]),"+f"(d[108]),"+f"(d[109]),"+f"(d[110]),"+f"(d[111]),"+f"(d[112]),"+f"(d[113]),"+f"(d[114]),"+f"(d[115]),"+f"(d[116]),"+f"(d[117]),"+f"(d[118]),"+f"(d[119]),"+f"(d[120]),"+f"(d[121]),"+f"(d[122]),"+f"(d[123]),"+f"(d[124]),"+f"(d[125]),"+f"(d[126]),"+f"(d[127])
    : "l"(da), "l"(db), "r"(sd), "n"(TB));
}
template<int TB> __device__ __forceinline__ void wgmma_ss_192(float* d, uint64_t da, uint64_t db, int sd) {
  asm volatile("{\n.reg .pred p;\nsetp.ne.b32 p, %98, 0;\n"
    "wgmma.mma_async.sync.aligned.m64n192k16.f32.bf16.bf16 {%0,%1,%2,%3,%4,%5,%6,%7,%8,%9,%10,%11,%12,%13,%14,%15,%16,%17,%18,%19,%20,%21,%22,%23,%24,%25,%26,%27,%28,%29,%30,%31,%32,%33,%34,%35,%36,%37,%38,%39,%40,%41,%42,%43,%44,%45,%46,%47,%48,%49,%50,%51,%52,%53,%54,%55,%56,%57,%58,%59,%60,%61,%62,%63,%64,%65,%66,%67,%68,%69,%70,%71,%72,%73,%74,%75,%76,%77,%78,%79,%80,%81,%82,%83,%84,%85,%86,%87,%88,%89,%90,%91,%92,%93,%94,%95}, %96, %97, p, 1, 1, 0, %99;\n}\n"
    : "+f"(d[0]),"+f"(d[1]),"+f"(d[2]),"+f"(d[3]),"+f"(d[4]),"+f"(d[5]),"+f"(d[6]),"+f"(d[7]),"+f"(d[8]),"+f"(d[9]),"+f"(d[10]),"+f"(d[11]),"+f"(d[12]),"+f"(d[13]),"+f"(d[14]),"+f"(d[15]),"+f"(d[16]),"+f"(d[17]),"+f"(d[18]),"+f"(d[19]),"+f"(d[20]),"+f"(d[21]),"+f"(d[22]),"+f"(d[23]),"+f"(d[24]),"+f"(d[25]),"+f"(d[26]),"+f"(d[27]),"+f"(d[28]),"+f"(d[29]),"+f"(d[30]),"+f"(d[31]),"+f"(d[32]),"+f"(d[33]),"+f"(d[34]),"+f"(d[35]),"+f"(d[36]),"+f"(d[37]),"+f"(d[38]),"+f"(d[39]),"+f"(d[40]),"+f"(d[41]),"+f"(d[42]),"+f"(d[43]),"+f"(d[44]),"+f"(d[45]),"+f"(d[46]),"+f"(d[47]),"+f"(d[48]),"+f"(d[49]),"+f"(d[50]),"+f"(d[51]),"+f"(d[52]),"+f"(d[53]),"+f"(d[54]),"+f"(d[55]),"+f"(d[56]),"+f"(d[57]),"+f"(d[58]),"+f"(d[59]),"+f"(d[60]),"+f"(d[61]),"+f"(d[62]),"+f"(d[63]),"+f"(d[64]),"+f"(d[65]),"+f"(d[66]),"+f"(d[67]),"+f"(d[68]),"+f"(d[69]),"+f"(d[70]),"+f"(d[71]),"+f"(d[72]),"+f"(d[73]),"+f"(d[74]),"+f"(d[75]),"+f"(d[76]),"+f"(d[77]),"+f"(d[78]),"+f"(d[79]),"+f"(d[80]),"+f"(d[81]),"+f"(d[82]),"+f"(d[83]),"+f"(d[84]),"+f"(d[85]),"+f"(d[86]),"+f"(d[87]),"+f"(d[88]),"+f"(d[89]),"+f"(d[90]),"+f"(d[91]),"+f"(d[92]),"+f"(d[93]),"+f"(d[94]),"+f"(d[95])
    : "l"(da), "l"(db), "r"(sd), "n"(TB));
}
template<int TB> __device__ __forceinline__ void wgmma_ss_112(float* d, uint64_t da, uint64_t db, int sd) {
  asm volatile("{\n.reg .pred p;\nsetp.ne.b32 p, %58, 0;\n"
    "wgmma.mma_async.sync.aligned.m64n112k16.f32.bf16.bf16 {%0,%1,%2,%3,%4,%5,%6,%7,%8,%9,%10,%11,%12,%13,%14,%15,%16,%17,%18,%19,%20,%21,%22,%23,%24,%25,%26,%27,%28,%29,%30,%31,%32,%33,%34,%35,%36,%37,%38,%39,%40,%41,%42,%43,%44,%45,%46,%47,%48,%49,%50,%51,%52,%53,%54,%55}, %56, %57, p, 1, 1, 0, %59;\n}\n"
    : "+f"(d[0]),"+f"(d[1]),"+f"(d[2]),"+f"(d[3]),"+f"(d[4]),"+f"(d[5]),"+f"(d[6]),"+f"(d[7]),"+f"(d[8]),"+f"(d[9]),"+f"(d[10]),"+f"(d[11]),"+f"(d[12]),"+f"(d[13]),"+f"(d[14]),"+f"(d[15]),"+f"(d[16]),"+f"(d[17]),"+f"(d[18]),"+f"(d[19]),"+f"(d[20]),"+f"(d[21]),"+f"(d[22]),"+f"(d[23]),"+f"(d[24]),"+f"(d[25]),"+f"(d[26]),"+f"(d[27]),"+f"(d[28]),"+f"(d[29]),"+f"(d[30]),"+f"(d[31]),"+f"(d[32]),"+f"(d[33]),"+f"(d[34]),"+f"(d[35]),"+f"(d[36]),"+f"(d[37]),"+f"(d[38]),"+f"(d[39]),"+f"(d[40]),"+f"(d[41]),"+f"(d[42]),"+f"(d[43]),"+f"(d[44]),"+f"(d[45]),"+f"(d[46]),"+f"(d[47]),"+f"(d[48]),"+f"(d[49]),"+f"(d[50]),"+f"(d[51]),"+f"(d[52]),"+f"(d[53]),"+f"(d[54]),"+f"(d[55])
    : "l"(da), "l"(db), "r"(sd), "n"(TB));
}
template<int TB> __device__ __forceinline__ void wgmma_rs_112(float* d, uint32_t a0, uint32_t a1, uint32_t a2, uint32_t a3, uint64_t db, int sd) {
  asm volatile("{\n.reg .pred p;\nsetp.ne.b32 p, %61, 0;\n"
    "wgmma.mma_async.sync.aligned.m64n112k16.f32.bf16.bf16 {%0,%1,%2,%3,%4,%5,%6,%7,%8,%9,%10,%11,%12,%13,%14,%15,%16,%17,%18,%19,%20,%21,%22,%23,%24,%25,%26,%27,%28,%29,%30,%31,%32,%33,%34,%35,%36,%37,%38,%39,%40,%41,%42,%43,%44,%45,%46,%47,%48,%49,%50,%51,%52,%53,%54,%55}, {%56,%57,%58,%59}, %60, p, 1, 1, %62;\n}\n"
    : "+f"(d[0]),"+f"(d[1]),"+f"(d[2]),"+f"(d[3]),"+f"(d[4]),"+f"(d[5]),"+f"(d[6]),"+f"(d[7]),"+f"(d[8]),"+f"(d[9]),"+f"(d[10]),"+f"(d[11]),"+f"(d[12]),"+f"(d[13]),"+f"(d[14]),"+f"(d[15]),"+f"(d[16]),"+f"(d[17]),"+f"(d[18]),"+f"(d[19]),"+f"(d[20]),"+f"(d[21]),"+f"(d[22]),"+f"(d[23]),"+f"(d[24]),"+f"(d[25]),"+f"(d[26]),"+f"(d[27]),"+f"(d[28]),"+f"(d[29]),"+f"(d[30]),"+f"(d[31]),"+f"(d[32]),"+f"(d[33]),"+f"(d[34]),"+f"(d[35]),"+f"(d[36]),"+f"(d[37]),"+f"(d[38]),"+f"(d[39]),"+f"(d[40]),"+f"(d[41]),"+f"(d[42]),"+f"(d[43]),"+f"(d[44]),"+f"(d[45]),"+f"(d[46]),"+f"(d[47]),"+f"(d[48]),"+f"(d[49]),"+f"(d[50]),"+f"(d[51]),"+f"(d[52]),"+f"(d[53]),"+f"(d[54]),"+f"(d[55])
    : "r"(a0), "r"(a1), "r"(a2), "r"(a3), "l"(db), "r"(sd), "n"(TB));
}

constexpr int DM = 448;
constexpr int NCTA = 128;
constexpr uint32_t SENT = 0xFFFFFFFFu;
constexpr int SPIN_LIMIT = 1 << 22;

constexpr uint32_t OFF_X = 0, OFF_Y = 114688, OFF_MISC = 229376, SMEM_BYTES = 232448;
constexpr uint32_t Y_VR = 0, Y_K = 28672, Y_KOWN = 57344, Y_VOWN = 71680, Y_Q = 86016;
constexpr uint32_t X_WO = 49152;
constexpr uint32_t M_BAR = OFF_MISC;
constexpr uint32_t M_ST = OFF_MISC + 512;
constexpr uint32_t M_G = OFF_MISC + 2304;
constexpr uint32_t M_RED = OFF_MISC + 2752;
constexpr uint32_t M_EPOCH = OFF_MISC + 2880;
enum { B_MOD1 = 0, B_MOD2, B_FULLK, B_FULLV, B_FULLQ, B_EMPTYK = B_FULLQ + 7, B_VDONE = B_EMPTYK + 7, B_KRFULL, B_VRFULL,
       B_WOFULL, B_FULL, B_EMPTY = B_FULL + 12, B_PUBK = B_EMPTY + 12, B_PUBV, B_PUBA, B_PUBB, B_PEER, B_XCH, B_DONE = B_XCH + 2, B_COUNT };

__device__ uint32_t g_ticket;
__device__ uint32_t g_mod[6 * DM];
__device__ uint32_t g_flagK[16 * 8 * 8], g_flagV[16 * 8 * 8], g_flagH[16 * 8 * 2 * 8], g_cntR[16 * 8];
__device__ __align__(128) uint32_t g_kv[16 * 8 * 2 * 3584];
__device__ __align__(128) uint4 g_o[32 * 16 * 2 * 128];
__device__ __align__(128) uint4 g_x1[32 * 8 * 4 * 128];
__device__ __align__(128) uint32_t g_h2[16 * 224 * 512];
#define PROF(role, id)
#define PROFC(id)

struct alignas(64) Params {
    CUtensorMap qkv, wo, ga, ua, gb, ub, dn;
    const bf16 *x, *c, *wmod, *wg, *wu, *wd, *wop;
    bf16* out;
};

__device__ __forceinline__ void mbar_init(uint32_t bar, int cnt) { asm volatile("mbarrier.init.shared::cta.b64 [%0], %1;" ::"r"(bar), "r"(cnt) : "memory"); }
__device__ __forceinline__ void mbar_expect_tx(uint32_t bar, uint32_t bytes) { asm volatile("mbarrier.arrive.expect_tx.shared::cta.b64 _, [%0], %1;" ::"r"(bar), "r"(bytes) : "memory"); }
__device__ __forceinline__ void mbar_arrive(uint32_t bar) { asm volatile("mbarrier.arrive.shared::cta.b64 _, [%0];" ::"r"(bar) : "memory"); }
__device__ __forceinline__ void mbar_wait(uint32_t bar, uint32_t parity) {
    uint32_t ok; int n = 0;
    do {
        asm volatile("{\n.reg .pred p;\nmbarrier.try_wait.parity.shared::cta.b64 p, [%1], %2;\nselp.u32 %0, 1, 0, p;\n}" : "=r"(ok) : "r"(bar), "r"(parity) : "memory");
        if (++n > SPIN_LIMIT) __trap();
    } while (!ok);
}
__device__ __forceinline__ void mbar_wait_cluster(uint32_t bar, uint32_t parity) {
    uint32_t ok; int n = 0;
    do {
        asm volatile("{\n.reg .pred p;\nmbarrier.try_wait.parity.acquire.cluster.shared::cta.b64 p, [%1], %2;\nselp.u32 %0, 1, 0, p;\n}" : "=r"(ok) : "r"(bar), "r"(parity) : "memory");
        if (++n > SPIN_LIMIT) __trap();
    } while (!ok);
}
__device__ __forceinline__ void warp_arrive(uint32_t bar) { __syncwarp(); if ((threadIdx.x & 31) == 0) mbar_arrive(bar); }
__device__ __forceinline__ void bar_sync(int id, int n) { asm volatile("bar.sync %0, %1;" ::"r"(id), "r"(n) : "memory"); }
__device__ __forceinline__ void bar_arrive(int id, int n) { asm volatile("bar.arrive %0, %1;" ::"r"(id), "r"(n) : "memory"); }
__device__ __forceinline__ void fence_async_smem() { asm volatile("fence.proxy.async.shared::cta;" ::: "memory"); }
__device__ __forceinline__ void fence_async_global() { asm volatile("fence.proxy.async.global;" ::: "memory"); }
__device__ __forceinline__ void fence_gpu() { asm volatile("fence.acq_rel.gpu;" ::: "memory"); }
__device__ __forceinline__ void tma3(uint32_t dst, const CUtensorMap* m, int c0, int c1, int c2, uint32_t bar) {
    asm volatile("cp.async.bulk.tensor.3d.shared::cluster.global.mbarrier::complete_tx::bytes [%0], [%1, {%3, %4, %5}], [%2];"
                 ::"r"(dst), "l"(m), "r"(bar), "r"(c0), "r"(c1), "r"(c2) : "memory");
}
__device__ __forceinline__ void bulk_load(uint32_t dst, const void* src, uint32_t bytes, uint32_t bar) {
    asm volatile("cp.async.bulk.shared::cluster.global.mbarrier::complete_tx::bytes [%0], [%1], %2, [%3];" ::"r"(dst), "l"(src), "r"(bytes), "r"(bar) : "memory");
}
__device__ __forceinline__ void l2_prefetch(const void* src, uint32_t bytes) { asm volatile("cp.async.bulk.prefetch.L2.global [%0], %1;" ::"l"(src), "r"(bytes) : "memory"); }
__device__ __forceinline__ uint32_t ld_relaxed(const uint32_t* p) { uint32_t v; asm volatile("ld.relaxed.gpu.global.u32 %0, [%1];" : "=r"(v) : "l"(p) : "memory"); return v; }
__device__ __forceinline__ void st_relaxed(uint32_t* p, uint32_t v) { asm volatile("st.relaxed.gpu.global.u32 [%0], %1;" ::"l"(p), "r"(v) : "memory"); }
__device__ __forceinline__ uint4 ld_relaxed4(const uint4* p) { uint4 v; asm volatile("ld.relaxed.gpu.global.v4.u32 {%0,%1,%2,%3}, [%4];" : "=r"(v.x), "=r"(v.y), "=r"(v.z), "=r"(v.w) : "l"(p) : "memory"); return v; }
__device__ __forceinline__ void st_relaxed4(uint4* p, uint4 v) { asm volatile("st.relaxed.gpu.global.v4.u32 [%0], {%1,%2,%3,%4};" ::"l"(p), "r"(v.x), "r"(v.y), "r"(v.z), "r"(v.w) : "memory"); }
__device__ __forceinline__ uint4 ldg_nc4(const void* p) { uint4 v; asm volatile("ld.global.nc.L1::no_allocate.v4.u32 {%0,%1,%2,%3}, [%4];" : "=r"(v.x), "=r"(v.y), "=r"(v.z), "=r"(v.w) : "l"(p)); return v; }
__device__ __forceinline__ uint32_t ldg_nc(const void* p) { uint32_t v; asm volatile("ld.global.nc.u32 %0, [%1];" : "=r"(v) : "l"(p)); return v; }
__device__ __forceinline__ uint4 lds4(uint32_t a) { uint4 v; asm volatile("ld.shared.v4.u32 {%0,%1,%2,%3}, [%4];" : "=r"(v.x), "=r"(v.y), "=r"(v.z), "=r"(v.w) : "r"(a) : "memory"); return v; }
__device__ __forceinline__ float2 lds2f(uint32_t a) { float2 v; asm volatile("ld.shared.v2.f32 {%0,%1}, [%2];" : "=f"(v.x), "=f"(v.y) : "r"(a) : "memory"); return v; }
__device__ __forceinline__ uint32_t lds1(uint32_t a) { uint32_t v; asm volatile("ld.shared.u32 %0, [%1];" : "=r"(v) : "r"(a) : "memory"); return v; }
__device__ __forceinline__ void sts4(uint32_t a, uint4 v) { asm volatile("st.shared.v4.u32 [%0], {%1,%2,%3,%4};" ::"r"(a), "r"(v.x), "r"(v.y), "r"(v.z), "r"(v.w) : "memory"); }
__device__ __forceinline__ void sts2(uint32_t a, uint32_t x, uint32_t y) { asm volatile("st.shared.v2.u32 [%0], {%1,%2};" ::"r"(a), "r"(x), "r"(y) : "memory"); }
__device__ __forceinline__ void sts1(uint32_t a, uint32_t v) { asm volatile("st.shared.u32 [%0], %1;" ::"r"(a), "r"(v) : "memory"); }
__device__ __forceinline__ void stsm4(uint32_t a, uint32_t r0, uint32_t r1, uint32_t r2, uint32_t r3) {
    asm volatile("stmatrix.sync.aligned.m8n8.x4.shared.b16 [%0], {%1,%2,%3,%4};" ::"r"(a), "r"(r0), "r"(r1), "r"(r2), "r"(r3) : "memory");
}
__device__ __forceinline__ uint32_t pack2(float lo, float hi) { uint32_t r; asm("cvt.rn.bf16x2.f32 %0, %1, %2;" : "=r"(r) : "f"(hi), "f"(lo)); return r; }
__device__ __forceinline__ uint32_t pack2_relu(float lo, float hi) { uint32_t r; asm("cvt.rn.relu.bf16x2.f32 %0, %1, %2;" : "=r"(r) : "f"(hi), "f"(lo)); return r; }
__device__ __forceinline__ uint32_t hfma2(uint32_t a, uint32_t b, uint32_t c) { uint32_t r; asm("fma.rn.bf16x2 %0, %1, %2, %3;" : "=r"(r) : "r"(a), "r"(b), "r"(c)); return r; }
__device__ __forceinline__ uint32_t hmul2(uint32_t a, uint32_t b) { uint32_t r; asm("mul.rn.bf16x2 %0, %1, %2;" : "=r"(r) : "r"(a), "r"(b)); return r; }
__device__ __forceinline__ float bf_lo(uint32_t v) { return __uint_as_float(v << 16); }
__device__ __forceinline__ float bf_hi(uint32_t v) { return __uint_as_float(v & 0xFFFF0000u); }
__device__ __forceinline__ float bf_round(float v) { return bf_lo(pack2(v, 0.f)); }
__device__ __forceinline__ float ex2(float x) { float r; asm("ex2.approx.ftz.f32 %0, %1;" : "=f"(r) : "f"(x)); return r; }
__device__ __forceinline__ void mma16816(float* d, uint32_t a0, uint32_t a1, uint32_t a2, uint32_t a3, uint32_t b0, uint32_t b1) {
    asm("mma.sync.aligned.m16n8k16.row.col.f32.bf16.bf16.f32 {%0,%1,%2,%3}, {%4,%5,%6,%7}, {%8,%9}, {%0,%1,%2,%3};"
        : "+f"(d[0]), "+f"(d[1]), "+f"(d[2]), "+f"(d[3]) : "r"(a0), "r"(a1), "r"(a2), "r"(a3), "r"(b0), "r"(b1));
}
__device__ __forceinline__ constexpr uint64_t dconst(uint32_t lbo, uint32_t sbo, uint32_t swz) {
    return ((uint64_t)(lbo >> 4) << 16) | ((uint64_t)(sbo >> 4) << 32) | ((uint64_t)swz << 62);
}
__device__ __forceinline__ uint64_t mkdesc(uint32_t addr, uint64_t c) { return c | (uint64_t)((addr & 0x3FFFF) >> 4); }
#define WG_FENCE() asm volatile("wgmma.fence.sync.aligned;" ::: "memory")
#define WG_COMMIT() asm volatile("wgmma.commit_group.sync.aligned;" ::: "memory")
#define WG_WAIT(n) asm volatile("wgmma.wait_group.sync.aligned %0;" ::"n"(n) : "memory")
template <int N> __device__ __forceinline__ void reg_fence(float* d) {
#pragma unroll
    for (int i = 0; i < N; i++) asm volatile("" : "+f"(d[i])::"memory");
}
__device__ __forceinline__ bool is_unset(uint4 v) { return max(max(v.x, v.y), max(v.z, v.w)) == SENT; }
__device__ __forceinline__ void wait_flag(const uint32_t* p, uint32_t target) {
    int n = 0;
    while ((int)(ld_relaxed(p) - target) < 0) { if (++n > SPIN_LIMIT) __trap(); }
}
__device__ __forceinline__ float silu_bf(uint32_t cbits) {
    float c = __uint_as_float(cbits << 16);
    return bf_round(c / (1.f + __expf(-c)));
}
__device__ __forceinline__ void fma8(float* acc, float s, uint4 w) {
    acc[0] += s * bf_lo(w.x); acc[1] += s * bf_hi(w.x); acc[2] += s * bf_lo(w.y); acc[3] += s * bf_hi(w.y);
    acc[4] += s * bf_lo(w.z); acc[5] += s * bf_hi(w.z); acc[6] += s * bf_lo(w.w); acc[7] += s * bf_hi(w.w);
}
__device__ __forceinline__ float reduce8(float* a, int lane) {
    bool h = lane & 16;
    float b[4];
#pragma unroll
    for (int i = 0; i < 4; i++) { float snd = h ? a[i] : a[i + 4]; float kp = h ? a[i + 4] : a[i]; b[i] = kp + __shfl_xor_sync(~0u, snd, 16); }
    h = lane & 8;
    float c[2];
#pragma unroll
    for (int i = 0; i < 2; i++) { float snd = h ? b[i] : b[i + 2]; float kp = h ? b[i + 2] : b[i]; c[i] = kp + __shfl_xor_sync(~0u, snd, 8); }
    h = lane & 4;
    float snd = h ? c[0] : c[1], kp = h ? c[1] : c[0];
    return kp + __shfl_xor_sync(~0u, snd, 4);
}

__global__ void __cluster_dims__(2, 1, 1) __launch_bounds__(384, 1) fused_block_kernel(const __grid_constant__ Params p) {
    extern __shared__ __align__(1024) unsigned char smem[];
    const uint32_t sb = (uint32_t)__cvta_generic_to_shared(smem);
    const int tid = threadIdx.x, lane = tid & 31, warp = tid >> 5;
    const int b = blockIdx.x, r = b >> 3, j = b & 7, kh = j & 1, nq = j >> 1;
    const int fs = 4 * kh + nq;
#define BAR(i) (sb + M_BAR + 8 * (i))

    if (tid == 256) {
        for (int i = 0; i < B_COUNT; i++) {
            int cnt = 1;
            if (i == B_MOD1) cnt = 3;
            if ((i >= B_EMPTYK && i <= B_VDONE) || (i >= B_EMPTY && i <= B_PEER) || i == B_DONE) cnt = 8;
            mbar_init(BAR(i), cnt);
        }
        asm volatile("fence.mbarrier_init.release.cluster;" ::: "memory");
        fence_async_smem();
    }

    if (warp < 8) {
        const int w = warp >> 2, wi = warp & 3, t = tid & 127, q = lane & 3, lr = lane >> 2;
        const int ra = 64 * w + 16 * wi + lr;
        uint4 xa[14], xb[14];
        const int par = lr & 1;
        {
            const uint4* row = (const uint4*)(p.x + (size_t)(128 * r + ra) * DM);
            const uint4* pe = row + q + 4 * par;
            const uint4* po = row + q + 4 * (1 - par);
#pragma unroll
            for (int i = 0; i < 14; i++) {
                const uint4* s = ((i & 1) ? po : pe) + 8 * (i >> 1);
                xa[i] = ldg_nc4(s);
                xb[i] = ldg_nc4(s + 8 * 56);
            }
        }
        bar_sync(0, 384);
        asm volatile("barrier.cluster.arrive.relaxed.aligned;" ::: "memory");
        asm volatile("setmaxnreg.inc.sync.aligned.u32 232;");
        PROFC(0);
        {
            float ds[2][4] = {}, da[2][4] = {}, db[2][4] = {};
            const uint32_t ONE2 = 0x3F803F80u;
#pragma unroll
            for (int i = 0; i < 14; i++) {
                mma16816(ds[0], xa[i].x, xb[i].x, xa[i].y, xb[i].y, ONE2, ONE2);
                mma16816(da[0], xa[i].x, xb[i].x, xa[i].y, xb[i].y, xa[i].x, xa[i].y);
                mma16816(db[0], xa[i].x, xb[i].x, xa[i].y, xb[i].y, xb[i].x, xb[i].y);
                mma16816(ds[1], xa[i].z, xb[i].z, xa[i].w, xb[i].w, ONE2, ONE2);
                mma16816(da[1], xa[i].z, xb[i].z, xa[i].w, xb[i].w, xa[i].z, xa[i].w);
                mma16816(db[1], xa[i].z, xb[i].z, xa[i].w, xb[i].w, xb[i].z, xb[i].w);
            }
            float qa = par ? da[0][1] + da[1][1] : da[0][0] + da[1][0];
            float qb = par ? db[0][3] + db[1][3] : db[0][2] + db[1][2];
            const int src = (lane & ~3) | (lr >> 1);
            qa = __shfl_sync(~0u, qa, src);
            qb = __shfl_sync(~0u, qb, src);
            const float ma = (ds[0][0] + ds[1][0]) * (1.f / DM), mb = (ds[0][2] + ds[1][2]) * (1.f / DM);
            const float rsa = bf_round(rsqrtf(fmaxf(qa * (1.f / DM) - ma * ma, 0.f) + 1e-5f));
            const float rsb = bf_round(rsqrtf(fmaxf(qb * (1.f / DM) - mb * mb, 0.f) + 1e-5f));
            const uint32_t ra2 = pack2(rsa, rsa), rb2 = pack2(rsb, rsb), na2 = pack2(-ma * rsa, -ma * rsa), nb2 = pack2(-mb * rsb, -mb * rsb);
#pragma unroll
            for (int i = 0; i < 14; i++) {
                xa[i].x = hfma2(xa[i].x, ra2, na2); xa[i].y = hfma2(xa[i].y, ra2, na2); xa[i].z = hfma2(xa[i].z, ra2, na2); xa[i].w = hfma2(xa[i].w, ra2, na2);
                xb[i].x = hfma2(xb[i].x, rb2, nb2); xb[i].y = hfma2(xb[i].y, rb2, nb2); xb[i].z = hfma2(xb[i].z, rb2, nb2); xb[i].w = hfma2(xb[i].w, rb2, nb2);
            }
            PROFC(1);
            mbar_wait(BAR(B_MOD1), 0);
            PROFC(2);
            const uint32_t ce = q + 4 * par, co = q + 4 * (1 - par);
            const uint32_t ae = sb + OFF_X + ra * 128 + ((ce ^ lr) << 4), ao = sb + OFF_X + ra * 128 + ((co ^ lr) << 4);
#pragma unroll
            for (int i = 0; i < 14; i++) {
                const uint32_t cofs = (((i & 1) ? co : ce) + 8 * (i >> 1)) * 16;
                const uint4 tt = lds4(sb + M_ST + cofs), ss = lds4(sb + M_ST + 896 + cofs);
                uint4 va, vb;
                va.x = hfma2(xa[i].x, ss.x, tt.x); va.y = hfma2(xa[i].y, ss.y, tt.y); va.z = hfma2(xa[i].z, ss.z, tt.z); va.w = hfma2(xa[i].w, ss.w, tt.w);
                vb.x = hfma2(xb[i].x, ss.x, tt.x); vb.y = hfma2(xb[i].y, ss.y, tt.y); vb.z = hfma2(xb[i].z, ss.z, tt.z); vb.w = hfma2(xb[i].w, ss.w, tt.w);
                const uint32_t a = ((i & 1) ? ao : ae) + (i >> 1) * 16384;
                sts4(a, va);
                sts4(a + 1024, vb);
            }
            fence_async_smem();
            bar_sync(1 + w, 128);
        }
        PROFC(3);
        constexpr uint64_t DA128 = dconst(16, 1024, 1), DB128 = dconst(4096, 1024, 1);
        uint32_t kp[14], vp[14];
        {
            float ak[28], av[28], aq[28];
            const uint64_t a0 = mkdesc(sb + OFF_X + w * 8192, DA128);
            const uint64_t bk0 = mkdesc(sb + OFF_Y + 57344, DB128), bv0 = mkdesc(sb + OFF_Y, DB128);
            uint32_t* kvg = g_kv + (size_t)(b * 2) * 3584 + (8 * w + 2 * wi) * 224 + lane;
            mbar_wait(BAR(B_FULLK), 0);
            reg_fence<28>(ak); reg_fence<28>(av); reg_fence<28>(aq);
#pragma unroll 1
            for (int kb = 0; kb < 7; kb++) {
                WG_FENCE();
#pragma unroll
                for (int ks = 0; ks < 4; ks++) wgmma_ss_56<1>(ak, a0 + kb * 1024 + ks * 2, bk0 + kb * 512 + ks * 128, (kb | ks) != 0);
                WG_COMMIT();
                if (kb > 0) { WG_WAIT(1); warp_arrive(BAR(B_EMPTYK + kb - 1)); }
            }
            mbar_wait(BAR(B_FULLV), 0);
            WG_FENCE();
#pragma unroll
            for (int ks = 0; ks < 8; ks++) wgmma_ss_56<1>(av, a0 + (ks >> 2) * 1024 + (ks & 3) * 2, bv0 + ks * 128, ks != 0);
            WG_COMMIT();
            WG_WAIT(1);
            reg_fence<28>(ak);
            warp_arrive(BAR(B_EMPTYK + 6));
#pragma unroll
            for (int g = 0; g < 7; g++) {
                kp[2 * g] = pack2(ak[4 * g], ak[4 * g + 1]); kp[2 * g + 1] = pack2(ak[4 * g + 2], ak[4 * g + 3]);
                kvg[g * 32] = kp[2 * g]; kvg[224 + g * 32] = kp[2 * g + 1];
            }
            warp_arrive(BAR(B_PUBK));
            PROFC(4);
#pragma unroll 1
            for (int kb = 2; kb < 7; kb++) {
                WG_FENCE();
#pragma unroll
                for (int ks = 0; ks < 4; ks++) wgmma_ss_56<1>(av, a0 + kb * 1024 + ks * 2, bv0 + kb * 512 + ks * 128, 1);
            }
            WG_COMMIT();
            mbar_wait(BAR(B_FULLQ), 0);
            mbar_wait(BAR(B_FULLQ + 1), 0);
            WG_FENCE();
#pragma unroll
            for (int ks = 0; ks < 8; ks++) wgmma_ss_56<1>(aq, a0 + (ks >> 2) * 1024 + (ks & 3) * 2, bk0 + ks * 128, ks != 0);
            WG_COMMIT();
            WG_WAIT(1);
            reg_fence<28>(av);
            warp_arrive(BAR(B_VDONE));
#pragma unroll
            for (int g = 0; g < 7; g++) {
                vp[2 * g] = pack2(av[4 * g], av[4 * g + 1]); vp[2 * g + 1] = pack2(av[4 * g + 2], av[4 * g + 3]);
                kvg[3584 + g * 32] = vp[2 * g]; kvg[3584 + 224 + g * 32] = vp[2 * g + 1];
            }
            warp_arrive(BAR(B_PUBV));
            PROFC(5);
#pragma unroll 1
            for (int kb = 2; kb < 7; kb++) {
                mbar_wait(BAR(B_FULLQ + kb), 0);
                WG_FENCE();
#pragma unroll
                for (int ks = 0; ks < 4; ks++) wgmma_ss_56<1>(aq, a0 + kb * 1024 + ks * 2, bk0 + kb * 512 + ks * 128, 1);
            }
            WG_COMMIT();
            WG_WAIT(0);
            reg_fence<28>(aq);
            __syncwarp();
            if (lane < 3) mbar_arrive(BAR(B_EMPTY + lane));
            bar_sync(3, 256);
            const uint32_t ko = sb + OFF_Y + Y_KOWN + (8 * w + 2 * wi) * 896 + lane * 4;
            const uint32_t qo = sb + OFF_Y + Y_Q + (8 * w + 2 * wi) * 1024 + lane * 4;
#pragma unroll
            for (int g = 0; g < 7; g++) {
                sts1(ko + g * 128, kp[2 * g]); sts1(ko + 896 + g * 128, kp[2 * g + 1]);
                sts1(ko + (Y_VOWN - Y_KOWN) + g * 128, vp[2 * g]); sts1(ko + (Y_VOWN - Y_KOWN) + 896 + g * 128, vp[2 * g + 1]);
                const uint32_t q0 = pack2(aq[4 * g], aq[4 * g + 1]), q1 = pack2(aq[4 * g + 2], aq[4 * g + 3]);
                if (g == 3) {
                    sts1(qo + 3 * 128, q < 2 ? q0 : 0u); sts1(qo + 1024 + 3 * 128, q < 2 ? q1 : 0u);
                    sts1(qo + 4 * 128, q < 2 ? 0u : q0); sts1(qo + 1024 + 4 * 128, q < 2 ? 0u : q1);
                } else {
                    const int ch = g < 3 ? g : g + 1;
                    sts1(qo + ch * 128, q0); sts1(qo + 1024 + ch * 128, q1);
                }
            }
            fence_async_smem();
            bar_sync(3, 256);
        }
        PROFC(6);
        mbar_wait(BAR(B_KRFULL), 0);
        PROFC(7);
#pragma unroll 1
        for (int hf = 0; hf < 2; hf++) {
            float s[160];
            const uint64_t qd = mkdesc(sb + OFF_Y + Y_Q + hf * 8192 + w * 512, dconst(128, 1024, 0));
            const uint64_t kd = mkdesc(sb + OFF_Y + Y_K + hf * 8 * 896 + w * 384, dconst(128, 896, 0));
            reg_fence<160>(s);
            WG_FENCE();
            wgmma_ss_160<0>(s, qd, kd, 0);
            wgmma_ss_160<0>(s, qd + 16, kd + 16, 1);
            wgmma_ss_160<0>(s + 80, qd, kd + 20 * 56, 0);
            wgmma_ss_160<0>(s + 80, qd + 16, kd + 20 * 56 + 16, 1);
            WG_COMMIT();
            WG_WAIT(0);
            reg_fence<160>(s);
            const float NEG = __int_as_float(0xFF800000);
            if (r < 2) {
                const int pmin = 16 - 8 * r - 4 * hf;
#pragma unroll
                for (int pp = 0; pp < 16; pp++)
                    if (pp < pmin) {
#pragma unroll
                        for (int i = 0; i < 8; i++) s[8 * pp + i] = NEG;
                    }
            }
            float m0 = NEG, m1 = NEG, m2 = NEG, m3 = NEG;
#pragma unroll
            for (int pp = 0; pp < 20; pp++) {
                float* e = s + 8 * pp;
                const bool act = pp < 3 ? pp >= wi : (pp > 16 ? pp <= wi + 16 : true);
                if (act) {
                    if (pp < 4 && pp == wi) {
                        if (!(2 * q > lr)) e[0] = NEG;
                        if (!(2 * q + 1 > lr)) e[1] = NEG;
                        e[2] = NEG; e[3] = NEG;
                        if (!(2 * q > lr)) e[6] = NEG;
                        if (!(2 * q + 1 > lr)) e[7] = NEG;
                    }
                    if (pp >= 16 && pp == wi + 16) {
                        if (2 * q > lr) e[0] = NEG;
                        if (2 * q + 1 > lr) e[1] = NEG;
                        e[4] = NEG; e[5] = NEG;
                        if (2 * q > lr) e[6] = NEG;
                        if (2 * q + 1 > lr) e[7] = NEG;
                    }
                    m0 = fmaxf(m0, fmaxf(e[0], e[1])); m1 = fmaxf(m1, fmaxf(e[2], e[3]));
                    m2 = fmaxf(m2, fmaxf(e[4], e[5])); m3 = fmaxf(m3, fmaxf(e[6], e[7]));
                }
            }
            float ma = fmaxf(m0, m2), mb = fmaxf(m1, m3);
            ma = fmaxf(ma, __shfl_xor_sync(~0u, ma, 1)); mb = fmaxf(mb, __shfl_xor_sync(~0u, mb, 1));
            ma = fmaxf(ma, __shfl_xor_sync(~0u, ma, 2)); mb = fmaxf(mb, __shfl_xor_sync(~0u, mb, 2));
            const float CS = 0.18898223650461361f * 1.4426950408889634f;
            const float na = -ma * CS, nb = -mb * CS;
            if (hf == 0) mbar_wait(BAR(B_VRFULL), 0);
            if (w == 1) bar_sync(5, 256);
            else if (hf == 1) bar_sync(4, 256);
            PROFC(8 + 3 * hf);
            float o[16];
            float sa0 = 0.f, sa1 = 0.f, sb0 = 0.f, sb1 = 0.f;
            uint32_t P[80];
            const uint32_t vbase = sb + OFF_Y + Y_VR + hf * 8 * 896 + w * 384;
            reg_fence<16>(o);
#pragma unroll
            for (int bt = 0; bt < 4; bt++) {
#pragma unroll
                for (int pi = 0; pi < 5; pi++) {
                    const int pp = bt * 5 + pi;
                    float* e = s + 8 * pp;
                    const bool act = pp < 3 ? pp >= wi : (pp > 16 ? pp <= wi + 16 : true);
                    if (act) {
                        const float e0 = ex2(fmaf(e[0], CS, na)), e1 = ex2(fmaf(e[1], CS, na)), e2 = ex2(fmaf(e[2], CS, nb)), e3 = ex2(fmaf(e[3], CS, nb));
                        const float e4 = ex2(fmaf(e[4], CS, na)), e5 = ex2(fmaf(e[5], CS, na)), e6 = ex2(fmaf(e[6], CS, nb)), e7 = ex2(fmaf(e[7], CS, nb));
                        sa0 += e0 + e1; sb0 += e2 + e3; sa1 += e4 + e5; sb1 += e6 + e7;
                        P[4 * pp] = pack2(e0, e1); P[4 * pp + 1] = pack2(e2, e3); P[4 * pp + 2] = pack2(e4, e5); P[4 * pp + 3] = pack2(e6, e7);
                    } else {
                        P[4 * pp] = 0; P[4 * pp + 1] = 0; P[4 * pp + 2] = 0; P[4 * pp + 3] = 0;
                    }
                }
                if (bt == 3) { if (w == 0) bar_arrive(5, 256); else if (hf == 0) bar_arrive(4, 256); }
                WG_FENCE();
#pragma unroll
                for (int pi = 0; pi < 5; pi++) {
                    const int pp = bt * 5 + pi;
                    uint32_t va = vbase + pp * 1792;
                    if (pp >= 16) va += Y_VOWN - 32 * 896;
                    else if (pp >= 12) va += hf * (Y_VOWN - 32 * 896);
                    wgmma_rs_32<1>(o, P[4 * pp], P[4 * pp + 1], P[4 * pp + 2], P[4 * pp + 3], mkdesc(va, dconst(896, 128, 0)), pp != 0);
                }
                WG_COMMIT();
            }
            PROFC(9 + 3 * hf);
            float sa = sa0 + sa1, sbb = sb0 + sb1;
            sa += __shfl_xor_sync(~0u, sa, 1); sbb += __shfl_xor_sync(~0u, sbb, 1);
            sa += __shfl_xor_sync(~0u, sa, 2); sbb += __shfl_xor_sync(~0u, sbb, 2);
            const float ia = 1.f / sa, ib = 1.f / sbb;
            WG_WAIT(0);
            reg_fence<16>(o);
            uint4 f0, f1;
            f0.x = pack2(o[0] * ia, o[1] * ia); f0.y = pack2(o[2] * ib, o[3] * ib); f0.z = pack2(o[4] * ia, o[5] * ia); f0.w = pack2(o[6] * ib, o[7] * ib);
            f1.x = pack2(o[8] * ia, o[9] * ia); f1.y = pack2(o[10] * ib, o[11] * ib); f1.z = pack2(o[12] * ia, o[13] * ia); f1.w = pack2(o[14] * ib, o[15] * ib);
            if (w == 0) { if (q >= 2) { f1.z = 0; f1.w = 0; } }
            else { if (q < 2) { f0.x = 0; f0.y = 0; } }
            uint4* og = g_o + (size_t)(((2 * r + hf) * 16 + 2 * j + w) * 2) * 128 + t;
            st_relaxed4(og, f0);
            st_relaxed4(og + 128, f1);
            PROFC(10 + 3 * hf);
        }
        bar_arrive(6 + w, 256);
        uint32_t x1p[14];
        {
            uint32_t xr[14];
            const bf16* xg = p.x + (size_t)(128 * r + ra) * DM + 56 * j + 2 * q;
#pragma unroll
            for (int g = 0; g < 7; g++) { xr[2 * g] = ldg_nc(xg + 8 * g); xr[2 * g + 1] = ldg_nc(xg + 8 * DM + 8 * g); }
            uint4 af[32];
            const uint4* og = g_o + (size_t)((2 * r + w) * 32) * 128 + t;
#pragma unroll
            for (int i = 0; i < 32; i++) af[i] = ld_relaxed4(og + i * 128);
            for (int n = 0;; n++) {
                bool again = false;
#pragma unroll
                for (int i = 0; i < 32; i++)
                    if (is_unset(af[i])) { af[i] = ld_relaxed4(og + i * 128); again = true; }
                if (!again) break;
                if (n > SPIN_LIMIT) __trap();
            }
            __syncwarp();
            PROFC(14);
            mbar_wait(BAR(B_WOFULL), 0);
            float ac[28];
            const uint64_t bd = mkdesc(sb + OFF_X + X_WO, DB128);
            reg_fence<28>(ac);
            WG_FENCE();
#pragma unroll
            for (int i = 0; i < 32; i++) wgmma_rs_56<1>(ac, af[i].x, af[i].y, af[i].z, af[i].w, bd + i * 128, i != 0);
            WG_COMMIT();
            mbar_wait(BAR(B_MOD2), 0);
            WG_WAIT(0);
            reg_fence<28>(ac);
            __syncwarp();
            if (lane < 4) mbar_arrive(BAR(B_EMPTY + 3 + lane));
            float s1a = 0.f, s2a = 0.f, s1b = 0.f, s2b = 0.f;
#pragma unroll
            for (int g = 0; g < 7; g++) {
                const float2 ga = lds2f(sb + M_G + (8 * g + 2 * q) * 4);
                x1p[2 * g] = pack2(fmaf(ga.x, ac[4 * g], bf_lo(xr[2 * g])), fmaf(ga.y, ac[4 * g + 1], bf_hi(xr[2 * g])));
                x1p[2 * g + 1] = pack2(fmaf(ga.x, ac[4 * g + 2], bf_lo(xr[2 * g + 1])), fmaf(ga.y, ac[4 * g + 3], bf_hi(xr[2 * g + 1])));
                const float u0 = bf_lo(x1p[2 * g]), u1 = bf_hi(x1p[2 * g]), u2 = bf_lo(x1p[2 * g + 1]), u3 = bf_hi(x1p[2 * g + 1]);
                s1a += u0 + u1; s2a += u0 * u0 + u1 * u1; s1b += u2 + u3; s2b += u2 * u2 + u3 * u3;
            }
            uint4* xo = g_x1 + (size_t)(((2 * r + w) * 8 + j) * 4) * 128 + t;
            st_relaxed4(xo, make_uint4(x1p[0], x1p[1], x1p[2], x1p[3]));
            st_relaxed4(xo + 128, make_uint4(x1p[4], x1p[5], x1p[6], x1p[7]));
            st_relaxed4(xo + 256, make_uint4(x1p[8], x1p[9], x1p[10], x1p[11]));
            float ka = (q & 1) ? s2a : s1a, kb2 = (q & 1) ? s2b : s1b;
            ka += __shfl_xor_sync(~0u, (q & 1) ? s1a : s2a, 1); kb2 += __shfl_xor_sync(~0u, (q & 1) ? s1b : s2b, 1);
            ka += __shfl_xor_sync(~0u, ka, 2); kb2 += __shfl_xor_sync(~0u, kb2, 2);
            st_relaxed4(xo + 384, make_uint4(x1p[12], x1p[13], __float_as_uint(ka), __float_as_uint(kb2)));
        }
        PROFC(15);
        {
            uint4 xf[32];
            const uint4* xg = g_x1 + (size_t)((2 * r + w) * 32) * 128 + t;
#pragma unroll
            for (int i = 0; i < 32; i++) xf[i] = ld_relaxed4(xg + i * 128);
            for (int n = 0;; n++) {
                bool again = false;
#pragma unroll
                for (int i = 0; i < 32; i++)
                    if (is_unset(xf[i])) { xf[i] = ld_relaxed4(xg + i * 128); again = true; }
                if (!again) break;
                if (n > SPIN_LIMIT) __trap();
            }
            __syncwarp();
            PROFC(16);
            float ka = 0.f, kb2 = 0.f;
#pragma unroll
            for (int jj = 0; jj < 8; jj++) { ka += __uint_as_float(xf[4 * jj + 3].z); kb2 += __uint_as_float(xf[4 * jj + 3].w); }
            const float oa = __shfl_xor_sync(~0u, ka, 1), ob = __shfl_xor_sync(~0u, kb2, 1);
            const float ma = ((q & 1) ? oa : ka) * (1.f / DM), mb = ((q & 1) ? ob : kb2) * (1.f / DM);
            const float qa = ((q & 1) ? ka : oa) * (1.f / DM), qb = ((q & 1) ? kb2 : ob) * (1.f / DM);
            const float rsa = bf_round(rsqrtf(fmaxf(qa - ma * ma, 0.f) + 1e-5f)), rsb = bf_round(rsqrtf(fmaxf(qb - mb * mb, 0.f) + 1e-5f));
            const uint32_t ra2 = pack2(rsa, rsa), rb2 = pack2(rsb, rsb), na2 = pack2(-ma * rsa, -ma * rsa), nb2 = pack2(-mb * rsb, -mb * rsb);
            bar_sync(7 - w, 256);
            const uint32_t lx = (lane >> 4) ^ (lane & 7);
            const uint32_t hb = sb + OFF_Y + (64 * w + 16 * wi + ((lane >> 3) & 1) * 8 + (lane & 7)) * 128;
            const uint32_t* xw = (const uint32_t*)xf;
#pragma unroll
            for (int G = 0; G < 56; G += 2) {
                const uint4 st = lds4(sb + M_ST + (G >> 1) * 64 + q * 16);
                const int i0 = (G / 7) * 16 + (G % 7) * 2, i1 = ((G + 1) / 7) * 16 + ((G + 1) % 7) * 2;
                const uint32_t h0 = hfma2(hfma2(xw[i0], ra2, na2), st.x, st.y), h1 = hfma2(hfma2(xw[i0 + 1], rb2, nb2), st.x, st.y);
                const uint32_t h2 = hfma2(hfma2(xw[i1], ra2, na2), st.z, st.w), h3 = hfma2(hfma2(xw[i1 + 1], rb2, nb2), st.z, st.w);
                stsm4(hb + (G >> 3) * 16384 + (((G & 7) ^ lx) << 4), h0, h1, h2, h3);
            }
            fence_async_smem();
            bar_sync(1 + w, 128);
        }
        PROFC(17);
        uint32_t h2a[32], h2b[24];
        const int fa = 224 * fs + ((fs & 1) ? 96 : 0), fb = 224 * fs + ((fs & 1) ? 0 : 128);
        uint32_t* h2g = g_h2 + (size_t)r * (224 * 512) + (8 * w + 2 * wi) * 32 + lane;
        {
            const uint64_t a0 = mkdesc(sb + OFF_Y + w * 8192, DA128);
            {
                float ac[128];
                reg_fence<128>(ac);
                WG_FENCE();
                int sl = 0, prev = 0;
#pragma unroll 1
                for (int s = 0; s < 14; s++) {
                    mbar_wait(BAR(B_FULL + sl), s >= 7);
                    const uint64_t ad = a0 + (s >> 1) * 1024 + (s & 1) * 4, bd = mkdesc(sb + OFF_X + sl * 16384, DB128);
                    WG_FENCE();
                    wgmma_ss_256<1>(ac, ad, bd, s != 0);
                    wgmma_ss_256<1>(ac, ad + 2, bd + 128, 1);
                    WG_COMMIT();
                    if (s > 0) { WG_WAIT(1); warp_arrive(BAR(B_EMPTY + prev)); }
                    prev = sl; sl = sl == 6 ? 0 : sl + 1;
                }
                WG_WAIT(0);
                reg_fence<128>(ac);
                warp_arrive(BAR(B_EMPTY + 6));
                PROFC(18);
#pragma unroll
                for (int g = 0; g < 16; g++) {
                    h2a[2 * g] = hmul2(pack2_relu(ac[4 * g], ac[4 * g + 1]), pack2(ac[64 + 4 * g], ac[64 + 4 * g + 1]));
                    h2a[2 * g + 1] = hmul2(pack2_relu(ac[4 * g + 2], ac[4 * g + 3]), pack2(ac[64 + 4 * g + 2], ac[64 + 4 * g + 3]));
                    h2g[(fa / 8 + g) * 512] = h2a[2 * g]; h2g[(fa / 8 + g) * 512 + 32] = h2a[2 * g + 1];
                }
                warp_arrive(BAR(B_PUBA));
            }
            PROFC(19);
            {
                float ac[96];
                reg_fence<96>(ac);
                WG_FENCE();
                int sl = 0, prev = 0;
#pragma unroll 1
                for (int s = 0; s < 14; s++) {
                    mbar_wait(BAR(B_FULL + sl), s >= 7);
                    const uint64_t ad = a0 + (s >> 1) * 1024 + (s & 1) * 4, bd = mkdesc(sb + OFF_X + sl * 16384, dconst(2048, 512, 2));
                    WG_FENCE();
                    wgmma_ss_192<1>(ac, ad, bd, s != 0);
                    wgmma_ss_192<1>(ac, ad + 2, bd + 64, 1);
                    WG_COMMIT();
                    if (s > 0) { WG_WAIT(1); warp_arrive(BAR(B_EMPTY + prev)); }
                    prev = sl; sl = sl == 6 ? 0 : sl + 1;
                }
                WG_WAIT(0);
                reg_fence<96>(ac);
                __syncwarp();
                if (lane < 6) mbar_arrive(BAR(B_EMPTY + 6 + lane));
                asm volatile("barrier.cluster.wait.aligned;" ::: "memory");
                if (lane == 0) {
                    uint32_t rb;
                    asm volatile("mapa.shared::cluster.u32 %0, %1, %2;" : "=r"(rb) : "r"(BAR(B_PEER)), "r"(kh ^ 1));
                    asm volatile("mbarrier.arrive.release.cluster.shared::cluster.b64 _, [%0];" ::"r"(rb) : "memory");
                }
                PROFC(20);
#pragma unroll
                for (int g = 0; g < 12; g++) {
                    h2b[2 * g] = hmul2(pack2_relu(ac[4 * g], ac[4 * g + 1]), pack2(ac[48 + 4 * g], ac[48 + 4 * g + 1]));
                    h2b[2 * g + 1] = hmul2(pack2_relu(ac[4 * g + 2], ac[4 * g + 3]), pack2(ac[48 + 4 * g + 2], ac[48 + 4 * g + 3]));
                    h2g[(fb / 8 + g) * 512] = h2b[2 * g]; h2g[(fb / 8 + g) * 512 + 32] = h2b[2 * g + 1];
                }
                warp_arrive(BAR(B_PUBB));
            }
        }
        PROFC(21);
        {
            float ac[56];
            reg_fence<56>(ac);
            WG_FENCE();
            constexpr uint64_t DAN = dconst(2048, 128, 0);
#pragma unroll 1
            for (int u = 0; u < 12; u++) {
                mbar_wait(BAR(B_FULL + u), 0);
                const uint32_t sl = sb + u * 16384;
                const uint64_t ad = mkdesc(sl + 8192 + w * 1024, DAN), bd = mkdesc(sl, DB128);
                WG_FENCE();
                wgmma_ss_112<1>(ac, ad, bd, u != 0);
                wgmma_ss_112<1>(ac, ad + 256, bd + 128, 1);
                WG_COMMIT();
                if (u > 0) { WG_WAIT(1); warp_arrive(BAR(B_EMPTY + u - 1)); }
            }
            PROFC(22);
#pragma unroll
            for (int u = 0; u < 7; u++) {
                mbar_wait(BAR(B_FULL + u), 1);
                const uint64_t bd = mkdesc(sb + u * 16384, DB128);
                const uint32_t* hh = u < 4 ? h2a + 8 * u : h2b + 8 * (u - 4);
                WG_FENCE();
                wgmma_rs_112<1>(ac, hh[0], hh[1], hh[2], hh[3], bd, 1);
                wgmma_rs_112<1>(ac, hh[4], hh[5], hh[6], hh[7], bd + 128, 1);
                WG_COMMIT();
                if (u > 0 && u < 5) { WG_WAIT(1); warp_arrive(BAR(B_EMPTY + u - 1)); }
                if (u == 0) { WG_WAIT(1); warp_arrive(BAR(B_EMPTY + 11)); }
            }
            PROFC(23);
#pragma unroll 1
            for (int u = 7; u < 16; u++) {
                const int sli = u < 12 ? u : u - 12;
                mbar_wait(BAR(B_FULL + sli), u < 12);
                const uint32_t sl = sb + sli * 16384;
                const uint64_t ad = mkdesc(sl + 8192 + w * 1024, DAN), bd = mkdesc(sl, DB128);
                WG_FENCE();
                wgmma_ss_112<1>(ac, ad, bd, 1);
                wgmma_ss_112<1>(ac, ad + 256, bd + 128, 1);
                WG_COMMIT();
            }
            mbar_wait_cluster(BAR(B_PEER), 0);
            WG_WAIT(0);
            reg_fence<56>(ac);
            PROFC(24);
            uint32_t rdst, rbar;
            asm volatile("mapa.shared::cluster.u32 %0, %1, %2;" : "=r"(rdst) : "r"(sb + OFF_Y + (5 + w) * 16384 + t * 16), "r"(kh ^ 1));
            asm volatile("mapa.shared::cluster.u32 %0, %1, %2;" : "=r"(rbar) : "r"(BAR(B_XCH + w)), "r"(kh ^ 1));
#pragma unroll
            for (int g = 0; g < 7; g++) {
                const float v0 = kh ? ac[4 * g] : ac[28 + 4 * g], v1 = kh ? ac[4 * g + 1] : ac[28 + 4 * g + 1];
                const float v2 = kh ? ac[4 * g + 2] : ac[28 + 4 * g + 2], v3 = kh ? ac[4 * g + 3] : ac[28 + 4 * g + 3];
                asm volatile("st.async.shared::cluster.mbarrier::complete_tx::bytes.v4.f32 [%0], {%1,%2,%3,%4}, [%5];"
                             ::"r"(rdst + g * 2048), "f"(v0), "f"(v1), "f"(v2), "f"(v3), "r"(rbar) : "memory");
            }
            mbar_wait_cluster(BAR(B_XCH + w), 0);
            PROFC(25);
            bf16* og = p.out + (size_t)(128 * r + ra) * DM + 56 * j + 2 * q;
#pragma unroll
            for (int g = 0; g < 7; g++) {
                const uint4 rv = lds4(sb + OFF_Y + (5 + w) * 16384 + t * 16 + g * 2048);
                const float2 gb = lds2f(sb + M_G + 224 + (8 * g + 2 * q) * 4);
                const float v0 = (kh ? ac[28 + 4 * g] : ac[4 * g]) + __uint_as_float(rv.x), v1 = (kh ? ac[28 + 4 * g + 1] : ac[4 * g + 1]) + __uint_as_float(rv.y);
                const float v2 = (kh ? ac[28 + 4 * g + 2] : ac[4 * g + 2]) + __uint_as_float(rv.z), v3 = (kh ? ac[28 + 4 * g + 3] : ac[4 * g + 3]) + __uint_as_float(rv.w);
                *(uint32_t*)(og + 8 * g) = pack2(fmaf(gb.x, v0, bf_lo(x1p[2 * g])), fmaf(gb.y, v1, bf_hi(x1p[2 * g])));
                *(uint32_t*)(og + 8 * DM + 8 * g) = pack2(fmaf(gb.x, v2, bf_lo(x1p[2 * g + 1])), fmaf(gb.y, v3, bf_hi(x1p[2 * g + 1])));
            }
        }
        PROFC(26);
        warp_arrive(BAR(B_DONE));
    } else {
        const int tl = tid - 288;
        uint4 wv[5];
        uint32_t cv[5];
        uint32_t ticket = 0;
        if (warp > 8) {
            if (b < 112) {
#pragma unroll
                for (int i = 0; i < 5; i++) {
                    const int row = min(tl + 96 * i, DM - 1);
                    wv[i] = ldg_nc4(p.wmod + (size_t)row * (6 * DM) + 8 * b);
                    cv[i] = (uint32_t)__ldg((const unsigned short*)p.c + row);
                }
            }
            if (tl == 0) ticket = atomicAdd(&g_ticket, 1u);
        }
        bar_sync(0, 384);
        asm volatile("barrier.cluster.arrive.relaxed.aligned;" ::: "memory");
        asm volatile("setmaxnreg.dec.sync.aligned.u32 40;");
        if (warp == 8) {
            if (lane == 0) {
                PROF(2, 0);
                mbar_expect_tx(BAR(B_FULLK), 57344);
                for (int kb = 0; kb < 7; kb++) tma3(sb + OFF_Y + 57344 + kb * 8192, &p.qkv, 0, 8 + j, 64 * kb, BAR(B_FULLK));
                mbar_expect_tx(BAR(B_FULLV), 57344);
                for (int kb = 0; kb < 7; kb++) tma3(sb + OFF_Y + kb * 8192, &p.qkv, 0, 16 + j, 64 * kb, BAR(B_FULLV));
                mbar_expect_tx(BAR(B_XCH), 14336);
                mbar_expect_tx(BAR(B_XCH + 1), 14336);
                if (b < 112) for (int i = 0; i < 4; i++) l2_prefetch(p.wmod + (size_t)(4 * b + i) * (6 * DM) + 2 * DM, 4 * DM * 2);
                for (int kb = 0; kb < 7; kb++) {
                    mbar_wait(BAR(B_EMPTYK + kb), 0);
                    mbar_expect_tx(BAR(B_FULLQ + kb), 8192);
                    tma3(sb + OFF_Y + 57344 + kb * 8192, &p.qkv, 0, j, 64 * kb, BAR(B_FULLQ + kb));
                }
                PROF(2, 1);
                const int fa = 224 * fs + ((fs & 1) ? 96 : 0), fb = 224 * fs + ((fs & 1) ? 0 : 128);
                mbar_wait(BAR(B_EMPTY), 0);
                mbar_expect_tx(BAR(B_WOFULL), 65536);
                for (int h = 0; h < 16; h++) tma3(sb + OFF_X + X_WO + h * 4096, &p.wo, 0, j, 28 * h - 4 * (h & 1), BAR(B_WOFULL));
                PROF(2, 2);
                int sl = 0;
                for (int s = 0; s < 28; s++) {
                    const int use = s >= 21 ? 3 : s >= 14 ? 2 : s >= 7 ? 1 : 0;
                    mbar_wait(BAR(B_EMPTY + sl), use & 1);
                    const uint32_t dst = sb + OFF_X + sl * 16384;
                    if (s < 14) {
                        mbar_expect_tx(BAR(B_FULL + sl), 16384);
                        tma3(dst, &p.ga, 0, 32 * s, fa >> 6, BAR(B_FULL + sl));
                        tma3(dst + 8192, &p.ua, 0, 32 * s, fa >> 6, BAR(B_FULL + sl));
                    } else {
                        mbar_expect_tx(BAR(B_FULL + sl), 12288);
                        tma3(dst, &p.gb, 0, 32 * (s - 14), fb >> 5, BAR(B_FULL + sl));
                        tma3(dst + 6144, &p.ub, 0, 32 * (s - 14), fb >> 5, BAR(B_FULL + sl));
                    }
                    sl = sl == 6 ? 0 : sl + 1;
                }
                PROF(2, 3);
                mbar_wait(BAR(B_MOD1), 0);
                const uint32_t target = lds1(sb + M_EPOCH) + 1;
                const uint32_t* h2g = g_h2 + (size_t)r * (224 * 512);
                sl = 0;
                for (int u = 0; u < 28; u++) {
                    int f; bool remote = true;
                    if (u < 12) {
                        const int ofs = 4 * kh + ((nq + 1 + (u >> 2)) & 3);
                        f = 224 * ofs + ((ofs & 1) ? 96 : 0) + 32 * (u & 3);
                        if ((u & 3) == 0) { wait_flag(&g_flagH[((r * 8 + ofs) * 2) * 8], target); fence_gpu(); fence_async_global(); }
                    } else if (u < 19) {
                        f = u < 16 ? fa + 32 * (u - 12) : fb + 32 * (u - 16);
                        remote = false;
                    } else {
                        const int v = u - 19, v3 = v >= 6 ? 2 : v >= 3 ? 1 : 0;
                        const int ofs = 4 * kh + ((nq + 1 + v3) & 3);
                        f = 224 * ofs + ((ofs & 1) ? 0 : 128) + 32 * (v - 3 * v3);
                        if (v == 3 * v3) { wait_flag(&g_flagH[((r * 8 + ofs) * 2 + 1) * 8], target); fence_gpu(); fence_async_global(); }
                    }
                    mbar_wait(BAR(B_EMPTY + sl), u >= 12 && u < 24);
                    const uint32_t dst = sb + sl * 16384;
                    mbar_expect_tx(BAR(B_FULL + sl), remote ? 16384 : 8192);
                    tma3(dst, &p.dn, 0, nq, f, BAR(B_FULL + sl));
                    tma3(dst + 4096, &p.dn, 64, nq, f, BAR(B_FULL + sl));
                    if (remote) bulk_load(dst + 8192, h2g + (size_t)(f >> 3) * 512, 8192, BAR(B_FULL + sl));
                    sl = sl == 11 ? 0 : sl + 1;
                }
                PROF(2, 4);
                mbar_wait(BAR(B_DONE), 0);
            }
        } else {
            if (tl == 0) sts1(sb + M_EPOCH, ticket / NCTA);
            if (b < 112) {
                float acc[8] = {};
#pragma unroll
                for (int i = 0; i < 5; i++) fma8(acc, (tl + 96 * i < DM) ? silu_bf(cv[i]) : 0.f, wv[i]);
                float v = reduce8(acc, lane);
                v += __shfl_xor_sync(~0u, v, 2);
                v += __shfl_xor_sync(~0u, v, 1);
                if ((lane & 3) == 0) sts1(sb + M_RED + ((warp - 9) * 8 + (lane >> 2)) * 4, __float_as_uint(v));
            }
            bar_sync(8, 96);
            const uint32_t epoch = lds1(sb + M_EPOCH);
            const uint32_t tag = (epoch + 1) & 0xFFFFu, target = epoch + 1;
            if (b < 112 && tl < 8) {
                const float v = __uint_as_float(lds1(sb + M_RED + tl * 4)) + __uint_as_float(lds1(sb + M_RED + 32 + tl * 4)) + __uint_as_float(lds1(sb + M_RED + 64 + tl * 4));
                st_relaxed(&g_mod[8 * b + tl], (pack2(v, 0.f) << 16) | tag);
            }
            PROF(3, 0);
#pragma unroll 1
            for (int i = tl; i < 224; i += 96) {
                uint4 v; int n = 0;
                do {
                    v = ld_relaxed4((const uint4*)g_mod + i);
                    if (++n > SPIN_LIMIT) __trap();
                } while (((v.x ^ tag) | (v.y ^ tag) | (v.z ^ tag) | (v.w ^ tag)) & 0xFFFFu);
                const float one = i >= 112 ? 1.f : 0.f;
                sts2(sb + M_ST + i * 8, pack2(bf_hi(v.x) + one, bf_hi(v.y) + one), pack2(bf_hi(v.z) + one, bf_hi(v.w) + one));
            }
            warp_arrive(BAR(B_MOD1));
            PROF(3, 1);
            if (warp == 9) {
                const uint4 sent = make_uint4(SENT, SENT, SENT, SENT);
#pragma unroll 1
                for (int hf = 0; hf < 2; hf++) {
                    uint4* o = g_o + (size_t)(((2 * r + hf) * 16 + 2 * j) * 2) * 128;
                    uint4* x1 = g_x1 + (size_t)(((2 * r + hf) * 8 + j) * 4) * 128;
#pragma unroll 4
                    for (int i = lane; i < 512; i += 32) { st_relaxed4(o + i, sent); st_relaxed4(x1 + i, sent); }
                }
                __syncwarp();
                if (lane == 0) {
                    fence_gpu();
                    asm volatile("red.relaxed.gpu.global.add.u32 [%0], 1;" ::"l"(&g_cntR[r * 8]) : "memory");
                    wait_flag(&g_cntR[r * 8], target * 8);
                    if (r >= 2) wait_flag(&g_flagK[((r - 2) * 8 + j) * 8], target);
                    if (r >= 1) wait_flag(&g_flagK[((r - 1) * 8 + j) * 8], target);
                    fence_gpu(); fence_async_global();
                    mbar_wait(BAR(B_VDONE), 0);
                    const uint32_t bytes = r >= 2 ? 28672 : r == 1 ? 14336 : 0;
                    mbar_expect_tx(BAR(B_KRFULL), bytes);
                    if (r >= 2) bulk_load(sb + OFF_Y + Y_K, g_kv + (size_t)((b - 16) * 2) * 3584, 14336, BAR(B_KRFULL));
                    if (r >= 1) bulk_load(sb + OFF_Y + Y_K + 14336, g_kv + (size_t)((b - 8) * 2) * 3584, 14336, BAR(B_KRFULL));
                    PROF(3, 2);
                    if (r >= 2) wait_flag(&g_flagV[((r - 2) * 8 + j) * 8], target);
                    if (r >= 1) wait_flag(&g_flagV[((r - 1) * 8 + j) * 8], target);
                    fence_gpu(); fence_async_global();
                    mbar_expect_tx(BAR(B_VRFULL), bytes);
                    if (r >= 2) bulk_load(sb + OFF_Y + Y_VR, g_kv + (size_t)((b - 16) * 2 + 1) * 3584, 14336, BAR(B_VRFULL));
                    if (r >= 1) bulk_load(sb + OFF_Y + Y_VR + 14336, g_kv + (size_t)((b - 8) * 2 + 1) * 3584, 14336, BAR(B_VRFULL));
                    PROF(3, 3);
                }
            } else if (warp == 10) {
                if (lane == 0) {
                    l2_prefetch((const char*)p.wop + (size_t)b * 3136, 3136);
                    l2_prefetch((const char*)p.wg + (size_t)b * 12544, 12544);
                    l2_prefetch((const char*)p.wu + (size_t)b * 12544, 12544);
                    l2_prefetch((const char*)p.wd + (size_t)b * 12544, 12544);
                    mbar_wait(BAR(B_PUBK), 0); fence_gpu(); st_relaxed(&g_flagK[b * 8], target);
                    mbar_wait(BAR(B_PUBV), 0); fence_gpu(); st_relaxed(&g_flagV[b * 8], target);
                    mbar_wait(BAR(B_PUBA), 0); fence_gpu(); st_relaxed(&g_flagH[((r * 8 + fs) * 2) * 8], target);
                    mbar_wait(BAR(B_PUBB), 0); fence_gpu(); st_relaxed(&g_flagH[((r * 8 + fs) * 2 + 1) * 8], target);
                }
            } else {
                if (b < 112) {
                    float acc[8] = {};
                    const bf16* wp = p.wmod + 2 * DM + 16 * b + 8 * (lane & 1);
#pragma unroll 1
                    for (int it = 0; it < 7; it++) {
                        uint4 v[4]; uint32_t c4[4];
#pragma unroll
                        for (int i = 0; i < 4; i++) {
                            const int row = (it * 4 + i) * 16 + (lane >> 1);
                            v[i] = ldg_nc4(wp + (size_t)row * (6 * DM));
                            c4[i] = (uint32_t)__ldg((const unsigned short*)p.c + row);
                        }
#pragma unroll
                        for (int i = 0; i < 4; i++) fma8(acc, silu_bf(c4[i]), v[i]);
                    }
                    float v = reduce8(acc, lane);
                    v += __shfl_xor_sync(~0u, v, 2);
                    if ((lane & 2) == 0) st_relaxed(&g_mod[2 * DM + 16 * b + 8 * (lane & 1) + (lane >> 2)], (pack2(v, 0.f) << 16) | tag);
                }
                PROF(3, 4);
                mbar_wait(BAR(B_PUBK), 0);
#pragma unroll 1
                for (int i = lane; i < 252; i += 32) {
                    const int wq = i < 224 ? 336 + i : (i < 238 ? 224 + 14 * j + (i - 224) : 560 + 14 * j + (i - 238));
                    uint4 v; int n = 0;
                    do {
                        v = ld_relaxed4((const uint4*)g_mod + wq);
                        if (++n > SPIN_LIMIT) __trap();
                    } while (((v.x ^ tag) | (v.y ^ tag) | (v.z ^ tag) | (v.w ^ tag)) & 0xFFFFu);
                    if (i < 224) {
                        const int isc = i >= 112, c4 = i - 112 * isc;
                        const float one = isc ? 1.f : 0.f;
                        const int G = c4 >> 1, qq = (c4 & 1) * 2;
                        const uint32_t a = sb + M_ST + (G >> 1) * 64 + qq * 16 + (G & 1) * 8 + (isc ? 0 : 4);
                        sts1(a, pack2(bf_hi(v.x) + one, bf_hi(v.y) + one));
                        sts1(a + 16, pack2(bf_hi(v.z) + one, bf_hi(v.w) + one));
                    } else {
                        sts4(sb + M_G + (i - 224) * 16, make_uint4(v.x & 0xFFFF0000u, v.y & 0xFFFF0000u, v.z & 0xFFFF0000u, v.w & 0xFFFF0000u));
                    }
                }
                warp_arrive(BAR(B_MOD2));
                PROF(3, 5);
            }
        }
    }
}

typedef CUresult (*EncodeFn)(CUtensorMap*, CUtensorMapDataType, cuuint32_t, void*, const cuuint64_t*, const cuuint64_t*, const cuuint32_t*,
                             const cuuint32_t*, CUtensorMapInterleave, CUtensorMapSwizzle, CUtensorMapL2promotion, CUtensorMapFloatOOBfill);

static void make_map(EncodeFn fn, CUtensorMap* m, const void* ptr, uint64_t d0, uint64_t d1, uint64_t d2, uint64_t s1, uint64_t s2,
                     uint32_t b0, uint32_t b1, uint32_t b2, CUtensorMapSwizzle sw) {
    cuuint64_t dims[3] = {d0, d1, d2}, strides[2] = {s1, s2};
    cuuint32_t box[3] = {b0, b1, b2}, es[3] = {1, 1, 1};
    CUresult rc = fn(m, CU_TENSOR_MAP_DATA_TYPE_BFLOAT16, 3, (void*)ptr, dims, strides, box, es, CU_TENSOR_MAP_INTERLEAVE_NONE, sw,
                     CU_TENSOR_MAP_L2_PROMOTION_L2_128B, CU_TENSOR_MAP_FLOAT_OOB_FILL_NONE);
    (void)rc;
}

extern "C" void kernel_launch(void* const* d_in, const int* in_sizes, int n_in, void* d_out, int out_size) {
    (void)in_sizes; (void)n_in; (void)out_size;
    static EncodeFn fn = nullptr;
    if (!fn) {
        cudaDriverEntryPointQueryResult st;
        cudaGetDriverEntryPoint("cuTensorMapEncodeTiled", (void**)&fn, cudaEnableDefault, &st);
        cudaFuncSetAttribute(fused_block_kernel, cudaFuncAttributeMaxDynamicSharedMemorySize, SMEM_BYTES);
    }
    Params p;
    p.x = (const bf16*)d_in[0];
    const bf16* wqkv = (const bf16*)d_in[1];
    p.wop = (const bf16*)d_in[2];
    p.wg = (const bf16*)d_in[4];
    p.wu = (const bf16*)d_in[5];
    p.wd = (const bf16*)d_in[6];
    p.c = (const bf16*)d_in[7];
    p.wmod = (const bf16*)d_in[8];
    p.out = (bf16*)d_out;
    make_map(fn, &p.qkv, wqkv, 56, 24, 448, 112, 2688, 64, 1, 64, CU_TENSOR_MAP_SWIZZLE_128B);
    make_map(fn, &p.wo, p.wop, 56, 8, 448, 112, 896, 64, 1, 32, CU_TENSOR_MAP_SWIZZLE_128B);
    make_map(fn, &p.ga, p.wg, 64, 448, 28, 3584, 128, 64, 32, 2, CU_TENSOR_MAP_SWIZZLE_128B);
    make_map(fn, &p.ua, p.wu, 64, 448, 28, 3584, 128, 64, 32, 2, CU_TENSOR_MAP_SWIZZLE_128B);
    make_map(fn, &p.gb, p.wg, 32, 448, 56, 3584, 64, 32, 32, 3, CU_TENSOR_MAP_SWIZZLE_64B);
    make_map(fn, &p.ub, p.wu, 32, 448, 56, 3584, 64, 32, 32, 3, CU_TENSOR_MAP_SWIZZLE_64B);
    make_map(fn, &p.dn, p.wd, 112, 4, 1792, 224, 896, 64, 1, 32, CU_TENSOR_MAP_SWIZZLE_128B);
    fused_block_kernel<<<NCTA, 384, SMEM_BYTES>>>(p);
}
```

```cpp
#include <cuda_runtime.h>
#include <cuda_bf16.h>
#include <cuda.h>
#include <stdint.h>

typedef __nv_bfloat16 bf16;

template<int TB> __device__ __forceinline__ void wgmma_rs_56(float* d, uint32_t a0, uint32_t a1, uint32_t a2, uint32_t a3, uint64_t db, int sd) {
  asm volatile("{\n.reg .pred p;\nsetp.ne.b32 p, %33, 0;\n"
    "wgmma.mma_async.sync.aligned.m64n56k16.f32.bf16.bf16 {%0,%1,%2,%3,%4,%5,%6,%7,%8,%9,%10,%11,%12,%13,%14,%15,%16,%17,%18,%19,%20,%21,%22,%23,%24,%25,%26,%27}, {%28,%29,%30,%31}, %32, p, 1, 1, %34;\n}\n"
    : "+f"(d[0]),"+f"(d[1]),"+f"(d[2]),"+f"(d[3]),"+f"(d[4]),"+f"(d[5]),"+f"(d[6]),"+f"(d[7]),"+f"(d[8]),"+f"(d[9]),"+f"(d[10]),"+f"(d[11]),"+f"(d[12]),"+f"(d[13]),"+f"(d[14]),"+f"(d[15]),"+f"(d[16]),"+f"(d[17]),"+f"(d[18]),"+f"(d[19]),"+f"(d[20]),"+f"(d[21]),"+f"(d[22]),"+f"(d[23]),"+f"(d[24]),"+f"(d[25]),"+f"(d[26]),"+f"(d[27])
    : "r"(a0), "r"(a1), "r"(a2), "r"(a3), "l"(db), "r"(sd), "n"(TB));
}
template<int TB> __device__ __forceinline__ void wgmma_ss_160(float* d, uint64_t da, uint64_t db, int sd) {
  asm volatile("{\n.reg .pred p;\nsetp.ne.b32 p, %82, 0;\n"
    "wgmma.mma_async.sync.aligned.m64n160k16.f32.bf16.bf16 {%0,%1,%2,%3,%4,%5,%6,%7,%8,%9,%10,%11,%12,%13,%14,%15,%16,%17,%18,%19,%20,%21,%22,%23,%24,%25,%26,%27,%28,%29,%30,%31,%32,%33,%34,%35,%36,%37,%38,%39,%40,%41,%42,%43,%44,%45,%46,%47,%48,%49,%50,%51,%52,%53,%54,%55,%56,%57,%58,%59,%60,%61,%62,%63,%64,%65,%66,%67,%68,%69,%70,%71,%72,%73,%74,%75,%76,%77,%78,%79}, %80, %81, p, 1, 1, 0, %83;\n}\n"
    : "+f"(d[0]),"+f"(d[1]),"+f"(d[2]),"+f"(d[3]),"+f"(d[4]),"+f"(d[5]),"+f"(d[6]),"+f"(d[7]),"+f"(d[8]),"+f"(d[9]),"+f"(d[10]),"+f"(d[11]),"+f"(d[12]),"+f"(d[13]),"+f"(d[14]),"+f"(d[15]),"+f"(d[16]),"+f"(d[17]),"+f"(d[18]),"+f"(d[19]),"+f"(d[20]),"+f"(d[21]),"+f"(d[22]),"+f"(d[23]),"+f"(d[24]),"+f"(d[25]),"+f"(d[26]),"+f"(d[27]),"+f"(d[28]),"+f"(d[29]),"+f"(d[30]),"+f"(d[31]),"+f"(d[32]),"+f"(d[33]),"+f"(d[34]),"+f"(d[35]),"+f"(d[36]),"+f"(d[37]),"+f"(d[38]),"+f"(d[39]),"+f"(d[40]),"+f"(d[41]),"+f"(d[42]),"+f"(d[43]),"+f"(d[44]),"+f"(d[45]),"+f"(d[46]),"+f"(d[47]),"+f"(d[48]),"+f"(d[49]),"+f"(d[50]),"+f"(d[51]),"+f"(d[52]),"+f"(d[53]),"+f"(d[54]),"+f"(d[55]),"+f"(d[56]),"+f"(d[57]),"+f"(d[58]),"+f"(d[59]),"+f"(d[60]),"+f"(d[61]),"+f"(d[62]),"+f"(d[63]),"+f"(d[64]),"+f"(d[65]),"+f"(d[66]),"+f"(d[67]),"+f"(d[68]),"+f"(d[69]),"+f"(d[70]),"+f"(d[71]),"+f"(d[72]),"+f"(d[73]),"+f"(d[74]),"+f"(d[75]),"+f"(d[76]),"+f"(d[77]),"+f"(d[78]),"+f"(d[79])
    : "l"(da), "l"(db), "r"(sd), "n"(TB));
}
template<int TB> __device__ __forceinline__ void wgmma_rs_32(float* d, uint32_t a0, uint32_t a1, uint32_t a2, uint32_t a3, uint64_t db, int sd) {
  asm volatile("{\n.reg .pred p;\nsetp.ne.b32 p, %21, 0;\n"
    "wgmma.mma_async.sync.aligned.m64n32k16.f32.bf16.bf16 {%0,%1,%2,%3,%4,%5,%6,%7,%8,%9,%10,%11,%12,%13,%14,%15}, {%16,%17,%18,%19}, %20, p, 1, 1, %22;\n}\n"
    : "+f"(d[0]),"+f"(d[1]),"+f"(d[2]),"+f"(d[3]),"+f"(d[4]),"+f"(d[5]),"+f"(d[6]),"+f"(d[7]),"+f"(d[8]),"+f"(d[9]),"+f"(d[10]),"+f"(d[11]),"+f"(d[12]),"+f"(d[13]),"+f"(d[14]),"+f"(d[15])
    : "r"(a0), "r"(a1), "r"(a2), "r"(a3), "l"(db), "r"(sd), "n"(TB));
}
template<int TB> __device__ __forceinline__ void wgmma_ss_256(float* d, uint64_t da, uint64_t db, int sd) {
  asm volatile("{\n.reg .pred p;\nsetp.ne.b32 p, %130, 0;\n"
    "wgmma.mma_async.sync.aligned.m64n256k16.f32.bf16.bf16 {%0,%1,%2,%3,%4,%5,%6,%7,%8,%9,%10,%11,%12,%13,%14,%15,%16,%17,%18,%19,%20,%21,%22,%23,%24,%25,%26,%27,%28,%29,%30,%31,%32,%33,%34,%35,%36,%37,%38,%39,%40,%41,%42,%43,%44,%45,%46,%47,%48,%49,%50,%51,%52,%53,%54,%55,%56,%57,%58,%59,%60,%61,%62,%63,%64,%65,%66,%67,%68,%69,%70,%71,%72,%73,%74,%75,%76,%77,%78,%79,%80,%81,%82,%83,%84,%85,%86,%87,%88,%89,%90,%91,%92,%93,%94,%95,%96,%97,%98,%99,%100,%101,%102,%103,%104,%105,%106,%107,%108,%109,%110,%111,%112,%113,%114,%115,%116,%117,%118,%119,%120,%121,%122,%123,%124,%125,%126,%127}, %128, %129, p, 1, 1, 0, %131;\n}\n"
    : "+f"(d[0]),"+f"(d[1]),"+f"(d[2]),"+f"(d[3]),"+f"(d[4]),"+f"(d[5]),"+f"(d[6]),"+f"(d[7]),"+f"(d[8]),"+f"(d[9]),"+f"(d[10]),"+f"(d[11]),"+f"(d[12]),"+f"(d[13]),"+f"(d[14]),"+f"(d[15]),"+f"(d[16]),"+f"(d[17]),"+f"(d[18]),"+f"(d[19]),"+f"(d[20]),"+f"(d[21]),"+f"(d[22]),"+f"(d[23]),"+f"(d[24]),"+f"(d[25]),"+f"(d[26]),"+f"(d[27]),"+f"(d[28]),"+f"(d[29]),"+f"(d[30]),"+f"(d[31]),"+f"(d[32]),"+f"(d[33]),"+f"(d[34]),"+f"(d[35]),"+f"(d[36]),"+f"(d[37]),"+f"(d[38]),"+f"(d[39]),"+f"(d[40]),"+f"(d[41]),"+f"(d[42]),"+f"(d[43]),"+f"(d[44]),"+f"(d[45]),"+f"(d[46]),"+f"(d[47]),"+f"(d[48]),"+f"(d[49]),"+f"(d[50]),"+f"(d[51]),"+f"(d[52]),"+f"(d[53]),"+f"(d[54]),"+f"(d[55]),"+f"(d[56]),"+f"(d[57]),"+f"(d[58]),"+f"(d[59]),"+f"(d[60]),"+f"(d[61]),"+f"(d[62]),"+f"(d[63]),"+f"(d[64]),"+f"(d[65]),"+f"(d[66]),"+f"(d[67]),"+f"(d[68]),"+f"(d[69]),"+f"(d[70]),"+f"(d[71]),"+f"(d[72]),"+f"(d[73]),"+f"(d[74]),"+f"(d[75]),"+f"(d[76]),"+f"(d[77]),"+f"(d[78]),"+f"(d[79]),"+f"(d[80]),"+f"(d[81]),"+f"(d[82]),"+f"(d[83]),"+f"(d[84]),"+f"(d[85]),"+f"(d[86]),"+f"(d[87]),"+f"(d[88]),"+f"(d[89]),"+f"(d[90]),"+f"(d[91]),"+f"(d[92]),"+f"(d[93]),"+f"(d[94]),"+f"(d[95]),"+f"(d[96]),"+f"(d[97]),"+f"(d[98]),"+f"(d[99]),"+f"(d[100]),"+f"(d[101]),"+f"(d[102]),"+f"(d[103]),"+f"(d[104]),"+f"(d[105]),"+f"(d[106]),"+f"(d[107]),"+f"(d[108]),"+f"(d[109]),"+f"(d[110]),"+f"(d[111]),"+f"(d[112]),"+f"(d[113]),"+f"(d[114]),"+f"(d[115]),"+f"(d[116]),"+f"(d[117]),"+f"(d[118]),"+f"(d[119]),"+f"(d[120]),"+f"(d[121]),"+f"(d[122]),"+f"(d[123]),"+f"(d[124]),"+f"(d[125]),"+f"(d[126]),"+f"(d[127])
    : "l"(da), "l"(db), "r"(sd), "n"(TB));
}
template<int TB> __device__ __forceinline__ void wgmma_ss_192(float* d, uint64_t da, uint64_t db, int sd) {
  asm volatile("{\n.reg .pred p;\nsetp.ne.b32 p, %98, 0;\n"
    "wgmma.mma_async.sync.aligned.m64n192k16.f32.bf16.bf16 {%0,%1,%2,%3,%4,%5,%6,%7,%8,%9,%10,%11,%12,%13,%14,%15,%16,%17,%18,%19,%20,%21,%22,%23,%24,%25,%26,%27,%28,%29,%30,%31,%32,%33,%34,%35,%36,%37,%38,%39,%40,%41,%42,%43,%44,%45,%46,%47,%48,%49,%50,%51,%52,%53,%54,%55,%56,%57,%58,%59,%60,%61,%62,%63,%64,%65,%66,%67,%68,%69,%70,%71,%72,%73,%74,%75,%76,%77,%78,%79,%80,%81,%82,%83,%84,%85,%86,%87,%88,%89,%90,%91,%92,%93,%94,%95}, %96, %97, p, 1, 1, 0, %99;\n}\n"
    : "+f"(d[0]),"+f"(d[1]),"+f"(d[2]),"+f"(d[3]),"+f"(d[4]),"+f"(d[5]),"+f"(d[6]),"+f"(d[7]),"+f"(d[8]),"+f"(d[9]),"+f"(d[10]),"+f"(d[11]),"+f"(d[12]),"+f"(d[13]),"+f"(d[14]),"+f"(d[15]),"+f"(d[16]),"+f"(d[17]),"+f"(d[18]),"+f"(d[19]),"+f"(d[20]),"+f"(d[21]),"+f"(d[22]),"+f"(d[23]),"+f"(d[24]),"+f"(d[25]),"+f"(d[26]),"+f"(d[27]),"+f"(d[28]),"+f"(d[29]),"+f"(d[30]),"+f"(d[31]),"+f"(d[32]),"+f"(d[33]),"+f"(d[34]),"+f"(d[35]),"+f"(d[36]),"+f"(d[37]),"+f"(d[38]),"+f"(d[39]),"+f"(d[40]),"+f"(d[41]),"+f"(d[42]),"+f"(d[43]),"+f"(d[44]),"+f"(d[45]),"+f"(d[46]),"+f"(d[47]),"+f"(d[48]),"+f"(d[49]),"+f"(d[50]),"+f"(d[51]),"+f"(d[52]),"+f"(d[53]),"+f"(d[54]),"+f"(d[55]),"+f"(d[56]),"+f"(d[57]),"+f"(d[58]),"+f"(d[59]),"+f"(d[60]),"+f"(d[61]),"+f"(d[62]),"+f"(d[63]),"+f"(d[64]),"+f"(d[65]),"+f"(d[66]),"+f"(d[67]),"+f"(d[68]),"+f"(d[69]),"+f"(d[70]),"+f"(d[71]),"+f"(d[72]),"+f"(d[73]),"+f"(d[74]),"+f"(d[75]),"+f"(d[76]),"+f"(d[77]),"+f"(d[78]),"+f"(d[79]),"+f"(d[80]),"+f"(d[81]),"+f"(d[82]),"+f"(d[83]),"+f"(d[84]),"+f"(d[85]),"+f"(d[86]),"+f"(d[87]),"+f"(d[88]),"+f"(d[89]),"+f"(d[90]),"+f"(d[91]),"+f"(d[92]),"+f"(d[93]),"+f"(d[94]),"+f"(d[95])
    : "l"(da), "l"(db), "r"(sd), "n"(TB));
}
template<int TB> __device__ __forceinline__ void wgmma_ss_112(float* d, uint64_t da, uint64_t db, int sd) {
  asm volatile("{\n.reg .pred p;\nsetp.ne.b32 p, %58, 0;\n"
    "wgmma.mma_async.sync.aligned.m64n112k16.f32.bf16.bf16 {%0,%1,%2,%3,%4,%5,%6,%7,%8,%9,%10,%11,%12,%13,%14,%15,%16,%17,%18,%19,%20,%21,%22,%23,%24,%25,%26,%27,%28,%29,%30,%31,%32,%33,%34,%35,%36,%37,%38,%39,%40,%41,%42,%43,%44,%45,%46,%47,%48,%49,%50,%51,%52,%53,%54,%55}, %56, %57, p, 1, 1, 0, %59;\n}\n"
    : "+f"(d[0]),"+f"(d[1]),"+f"(d[2]),"+f"(d[3]),"+f"(d[4]),"+f"(d[5]),"+f"(d[6]),"+f"(d[7]),"+f"(d[8]),"+f"(d[9]),"+f"(d[10]),"+f"(d[11]),"+f"(d[12]),"+f"(d[13]),"+f"(d[14]),"+f"(d[15]),"+f"(d[16]),"+f"(d[17]),"+f"(d[18]),"+f"(d[19]),"+f"(d[20]),"+f"(d[21]),"+f"(d[22]),"+f"(d[23]),"+f"(d[24]),"+f"(d[25]),"+f"(d[26]),"+f"(d[27]),"+f"(d[28]),"+f"(d[29]),"+f"(d[30]),"+f"(d[31]),"+f"(d[32]),"+f"(d[33]),"+f"(d[34]),"+f"(d[35]),"+f"(d[36]),"+f"(d[37]),"+f"(d[38]),"+f"(d[39]),"+f"(d[40]),"+f"(d[41]),"+f"(d[42]),"+f"(d[43]),"+f"(d[44]),"+f"(d[45]),"+f"(d[46]),"+f"(d[47]),"+f"(d[48]),"+f"(d[49]),"+f"(d[50]),"+f"(d[51]),"+f"(d[52]),"+f"(d[53]),"+f"(d[54]),"+f"(d[55])
    : "l"(da), "l"(db), "r"(sd), "n"(TB));
}
template<int TB> __device__ __forceinline__ void wgmma_rs_112(float* d, uint32_t a0, uint32_t a1, uint32_t a2, uint32_t a3, uint64_t db, int sd) {
  asm volatile("{\n.reg .pred p;\nsetp.ne.b32 p, %61, 0;\n"
    "wgmma.mma_async.sync.aligned.m64n112k16.f32.bf16.bf16 {%0,%1,%2,%3,%4,%5,%6,%7,%8,%9,%10,%11,%12,%13,%14,%15,%16,%17,%18,%19,%20,%21,%22,%23,%24,%25,%26,%27,%28,%29,%30,%31,%32,%33,%34,%35,%36,%37,%38,%39,%40,%41,%42,%43,%44,%45,%46,%47,%48,%49,%50,%51,%52,%53,%54,%55}, {%56,%57,%58,%59}, %60, p, 1, 1, %62;\n}\n"
    : "+f"(d[0]),"+f"(d[1]),"+f"(d[2]),"+f"(d[3]),"+f"(d[4]),"+f"(d[5]),"+f"(d[6]),"+f"(d[7]),"+f"(d[8]),"+f"(d[9]),"+f"(d[10]),"+f"(d[11]),"+f"(d[12]),"+f"(d[13]),"+f"(d[14]),"+f"(d[15]),"+f"(d[16]),"+f"(d[17]),"+f"(d[18]),"+f"(d[19]),"+f"(d[20]),"+f"(d[21]),"+f"(d[22]),"+f"(d[23]),"+f"(d[24]),"+f"(d[25]),"+f"(d[26]),"+f"(d[27]),"+f"(d[28]),"+f"(d[29]),"+f"(d[30]),"+f"(d[31]),"+f"(d[32]),"+f"(d[33]),"+f"(d[34]),"+f"(d[35]),"+f"(d[36]),"+f"(d[37]),"+f"(d[38]),"+f"(d[39]),"+f"(d[40]),"+f"(d[41]),"+f"(d[42]),"+f"(d[43]),"+f"(d[44]),"+f"(d[45]),"+f"(d[46]),"+f"(d[47]),"+f"(d[48]),"+f"(d[49]),"+f"(d[50]),"+f"(d[51]),"+f"(d[52]),"+f"(d[53]),"+f"(d[54]),"+f"(d[55])
    : "r"(a0), "r"(a1), "r"(a2), "r"(a3), "l"(db), "r"(sd), "n"(TB));
}

constexpr int DM = 448;
constexpr int NCTA = 128;
#define MAPPING 1
#define GRID 132
#define WMB 7
#define MAP_S 4
constexpr int SPIN_LIMIT = 1 << 22;

constexpr uint32_t OFF_X = 0, OFF_Y = 114688, OFF_MISC = 229376, SMEM_BYTES = 232448;
constexpr uint32_t Y_VR = 0, Y_K = 28672, Y_KOWN = 57344, Y_VOWN = 71680, Y_Q = 86016;
constexpr uint32_t HALF = 57344;
constexpr uint32_t M_BAR = OFF_MISC;
constexpr uint32_t M_ST = OFF_MISC + 512;
constexpr uint32_t M_G = OFF_MISC + 2304;
constexpr uint32_t M_RED = OFF_MISC + 2752;
constexpr uint32_t M_EPOCH = OFF_MISC + 3040;
enum { B_XFULL = 0, B_FULLK = 7, B_FULLV = 8, B_FULLQ, B_KRFULL, B_VRFULL, B_WOFULL, B_XCH, B_HRDY = B_XCH + 2, B_FULL = B_HRDY + 2,
       B_EMPTY = 32, B_XFREE = B_EMPTY + 12, B_KDONE, B_PUBK, B_PUBV, B_PUBA, B_PUBB, B_PEER, B_DONE,
       B_MOD1 = 56, B_MOD2, B_WMFREE, B_WMFULL };

__device__ uint32_t g_ticket;
__device__ __align__(128) uint32_t g_mod[8 * 6 * DM];
__device__ uint32_t g_flagK[16 * 8 * 8], g_flagV[16 * 8 * 8], g_flagH[16 * 8 * 2 * 8];
__device__ __align__(128) uint32_t g_kv[17 * 8 * 2 * 3584];
constexpr int XB = 34 * 32 * 128;
__device__ __align__(128) uint4 g_o[2 * XB];
__device__ __align__(128) uint4 g_x1[2 * XB];
__device__ __align__(128) uint32_t g_h2[17 * 224 * 512];
#define PROF(role, id)
#define PROFC(id)
#define PROFG(id)

struct alignas(64) Params {
    CUtensorMap wm, xm, qkv, wo, ga, ua, gb, ub, dn;
    const bf16 *x, *c, *wmod, *wg, *wu, *wd, *wop;
    bf16* out;
};

__device__ __forceinline__ void mbar_init(uint32_t bar, int cnt) { asm volatile("mbarrier.init.shared::cta.b64 [%0], %1;" ::"r"(bar), "r"(cnt) : "memory"); }
__device__ __forceinline__ void mbar_expect_tx(uint32_t bar, uint32_t bytes) { asm volatile("mbarrier.arrive.expect_tx.shared::cta.b64 _, [%0], %1;" ::"r"(bar), "r"(bytes) : "memory"); }
__device__ __forceinline__ void mbar_arrive(uint32_t bar) { asm volatile("mbarrier.arrive.shared::cta.b64 _, [%0];" ::"r"(bar) : "memory"); }
__device__ __forceinline__ void mbar_wait(uint32_t bar, uint32_t parity) {
    uint32_t ok; int n = 0;
    do {
        asm volatile("{\n.reg .pred p;\nmbarrier.try_wait.parity.shared::cta.b64 p, [%1], %2;\nselp.u32 %0, 1, 0, p;\n}" : "=r"(ok) : "r"(bar), "r"(parity) : "memory");
        if (++n > SPIN_LIMIT) __trap();
    } while (!ok);
}
__device__ __forceinline__ void mbar_wait_cluster(uint32_t bar, uint32_t parity) {
    uint32_t ok; int n = 0;
    do {
        asm volatile("{\n.reg .pred p;\nmbarrier.try_wait.parity.acquire.cluster.shared::cta.b64 p, [%1], %2;\nselp.u32 %0, 1, 0, p;\n}" : "=r"(ok) : "r"(bar), "r"(parity) : "memory");
        if (++n > SPIN_LIMIT) __trap();
    } while (!ok);
}
__device__ __forceinline__ void warp_arrive(uint32_t bar) {
    __syncwarp();
    asm volatile("{\n.reg .pred p;\nelect.sync _|p, 0xffffffff;\n@p mbarrier.arrive.shared::cta.b64 _, [%0];\n}" ::"r"(bar) : "memory");
}
__device__ __forceinline__ int fresh_tid() { int v; asm volatile("mov.u32 %0, %%tid.x;" : "=r"(v)); return v; }
__device__ __forceinline__ void bar_sync(int id, int n) { asm volatile("bar.sync %0, %1;" ::"r"(id), "r"(n) : "memory"); }
__device__ __forceinline__ void bar_arrive(int id, int n) { asm volatile("bar.arrive %0, %1;" ::"r"(id), "r"(n) : "memory"); }
__device__ __forceinline__ void fence_async_smem() { asm volatile("fence.proxy.async.shared::cta;" ::: "memory"); }
__device__ __forceinline__ void fence_async_global() { asm volatile("fence.proxy.async.global;" ::: "memory"); }
__device__ __forceinline__ void fence_gpu() { asm volatile("fence.acq_rel.gpu;" ::: "memory"); }
__device__ __forceinline__ void tma3(uint32_t dst, const CUtensorMap* m, int c0, int c1, int c2, uint32_t bar) {
    asm volatile("cp.async.bulk.tensor.3d.shared::cluster.global.mbarrier::complete_tx::bytes [%0], [%1, {%3, %4, %5}], [%2];"
                 ::"r"(dst), "l"(m), "r"(bar), "r"(c0), "r"(c1), "r"(c2) : "memory");
}
__device__ __forceinline__ void bulk_load(uint32_t dst, const void* src, uint32_t bytes, uint32_t bar) {
    asm volatile("cp.async.bulk.shared::cluster.global.mbarrier::complete_tx::bytes [%0], [%1], %2, [%3];" ::"r"(dst), "l"(src), "r"(bytes), "r"(bar) : "memory");
}
__device__ __forceinline__ void l2_prefetch(const void* src, uint32_t bytes) { asm volatile("cp.async.bulk.prefetch.L2.global [%0], %1;" ::"l"(src), "r"(bytes) : "memory"); }
__device__ __forceinline__ uint32_t ld_relaxed(const uint32_t* p) { uint32_t v; asm volatile("ld.relaxed.gpu.global.u32 %0, [%1];" : "=r"(v) : "l"(p) : "memory"); return v; }
__device__ __forceinline__ void st_relaxed(uint32_t* p, uint32_t v) { asm volatile("st.relaxed.gpu.global.u32 [%0], %1;" ::"l"(p), "r"(v) : "memory"); }
__device__ __forceinline__ uint4 ld_relaxed4(const uint4* p) { uint4 v; asm volatile("ld.relaxed.gpu.global.v4.u32 {%0,%1,%2,%3}, [%4];" : "=r"(v.x), "=r"(v.y), "=r"(v.z), "=r"(v.w) : "l"(p) : "memory"); return v; }
__device__ __forceinline__ void st_relaxed4(uint4* p, uint4 v) { asm volatile("st.relaxed.gpu.global.v4.u32 [%0], {%1,%2,%3,%4};" ::"l"(p), "r"(v.x), "r"(v.y), "r"(v.z), "r"(v.w) : "memory"); }
__device__ __forceinline__ uint4 ldg_nc4(const void* p) { uint4 v; asm volatile("ld.global.nc.L1::no_allocate.v4.u32 {%0,%1,%2,%3}, [%4];" : "=r"(v.x), "=r"(v.y), "=r"(v.z), "=r"(v.w) : "l"(p)); return v; }
__device__ __forceinline__ uint32_t ldg_nc(const void* p) { uint32_t v; asm volatile("ld.global.nc.u32 %0, [%1];" : "=r"(v) : "l"(p)); return v; }
__device__ __forceinline__ uint32_t ld_acquire(const uint32_t* p) { uint32_t v; asm volatile("ld.acquire.gpu.global.u32 %0, [%1];" : "=r"(v) : "l"(p) : "memory"); return v; }
__device__ __forceinline__ uint4 lds4(uint32_t a) { uint4 v; asm volatile("ld.shared.v4.u32 {%0,%1,%2,%3}, [%4];" : "=r"(v.x), "=r"(v.y), "=r"(v.z), "=r"(v.w) : "r"(a) : "memory"); return v; }
__device__ __forceinline__ float2 lds2f(uint32_t a) { float2 v; asm volatile("ld.shared.v2.f32 {%0,%1}, [%2];" : "=f"(v.x), "=f"(v.y) : "r"(a) : "memory"); return v; }
__device__ __forceinline__ uint32_t lds1(uint32_t a) { uint32_t v; asm volatile("ld.shared.u32 %0, [%1];" : "=r"(v) : "r"(a) : "memory"); return v; }
__device__ __forceinline__ void sts4(uint32_t a, uint4 v) { asm volatile("st.shared.v4.u32 [%0], {%1,%2,%3,%4};" ::"r"(a), "r"(v.x), "r"(v.y), "r"(v.z), "r"(v.w) : "memory"); }
__device__ __forceinline__ void sts2(uint32_t a, uint32_t x, uint32_t y) { asm volatile("st.shared.v2.u32 [%0], {%1,%2};" ::"r"(a), "r"(x), "r"(y) : "memory"); }
__device__ __forceinline__ void sts1(uint32_t a, uint32_t v) { asm volatile("st.shared.u32 [%0], %1;" ::"r"(a), "r"(v) : "memory"); }
__device__ __forceinline__ void stsm4(uint32_t a, uint32_t r0, uint32_t r1, uint32_t r2, uint32_t r3) {
    asm volatile("stmatrix.sync.aligned.m8n8.x4.shared.b16 [%0], {%1,%2,%3,%4};" ::"r"(a), "r"(r0), "r"(r1), "r"(r2), "r"(r3) : "memory");
}
__device__ __forceinline__ uint32_t pack2(float lo, float hi) { uint32_t r; asm("cvt.rn.bf16x2.f32 %0, %1, %2;" : "=r"(r) : "f"(hi), "f"(lo)); return r; }
__device__ __forceinline__ uint32_t pack2_relu(float lo, float hi) { uint32_t r; asm("cvt.rn.relu.bf16x2.f32 %0, %1, %2;" : "=r"(r) : "f"(hi), "f"(lo)); return r; }
__device__ __forceinline__ uint32_t hfma2(uint32_t a, uint32_t b, uint32_t c) { uint32_t r; asm("fma.rn.bf16x2 %0, %1, %2, %3;" : "=r"(r) : "r"(a), "r"(b), "r"(c)); return r; }
__device__ __forceinline__ uint32_t hmul2(uint32_t a, uint32_t b) { uint32_t r; asm("mul.rn.bf16x2 %0, %1, %2;" : "=r"(r) : "r"(a), "r"(b)); return r; }
__device__ __forceinline__ float bf_lo(uint32_t v) { return __uint_as_float(v << 16); }
__device__ __forceinline__ float bf_hi(uint32_t v) { return __uint_as_float(v & 0xFFFF0000u); }
__device__ __forceinline__ float bf_round(float v) { return bf_lo(pack2(v, 0.f)); }
__device__ __forceinline__ float ex2(float x) { float r; asm("ex2.approx.ftz.f32 %0, %1;" : "=f"(r) : "f"(x)); return r; }
__device__ __forceinline__ void mma16816(float* d, uint32_t a0, uint32_t a1, uint32_t a2, uint32_t a3, uint32_t b0, uint32_t b1) {
    asm("mma.sync.aligned.m16n8k16.row.col.f32.bf16.bf16.f32 {%0,%1,%2,%3}, {%4,%5,%6,%7}, {%8,%9}, {%0,%1,%2,%3};"
        : "+f"(d[0]), "+f"(d[1]), "+f"(d[2]), "+f"(d[3]) : "r"(a0), "r"(a1), "r"(a2), "r"(a3), "r"(b0), "r"(b1));
}
__device__ __forceinline__ void mma1688(float* d, uint32_t a0, uint32_t a1, uint32_t b0) {
    asm("mma.sync.aligned.m16n8k8.row.col.f32.bf16.bf16.f32 {%0,%1,%2,%3}, {%4,%5}, {%6}, {%0,%1,%2,%3};"
        : "+f"(d[0]), "+f"(d[1]), "+f"(d[2]), "+f"(d[3]) : "r"(a0), "r"(a1), "r"(b0));
}
__device__ __forceinline__ void ldsm4(uint32_t a, uint32_t* r) {
    asm volatile("ldmatrix.sync.aligned.m8n8.x4.shared.b16 {%0,%1,%2,%3}, [%4];" : "=r"(r[0]), "=r"(r[1]), "=r"(r[2]), "=r"(r[3]) : "r"(a) : "memory");
}
__device__ __forceinline__ uint2 ld_relaxed2(const void* p) { uint2 v; asm volatile("ld.relaxed.gpu.global.v2.u32 {%0,%1}, [%2];" : "=r"(v.x), "=r"(v.y) : "l"(p) : "memory"); return v; }
__device__ __forceinline__ void st_relaxed2(void* p, uint32_t x, uint32_t y) { asm volatile("st.relaxed.gpu.global.v2.u32 [%0], {%1,%2};" ::"l"(p), "r"(max(x, 1u)), "r"(max(y, 1u)) : "memory"); }
__device__ __forceinline__ constexpr uint64_t dconst(uint32_t lbo, uint32_t sbo, uint32_t swz) {
    return ((uint64_t)(lbo >> 4) << 16) | ((uint64_t)(sbo >> 4) << 32) | ((uint64_t)swz << 62);
}
__device__ __forceinline__ uint64_t mkdesc(uint32_t addr, uint64_t c) { return c | (uint64_t)((addr & 0x3FFFF) >> 4); }
#define WG_FENCE() asm volatile("wgmma.fence.sync.aligned;" ::: "memory")
#define WG_COMMIT() asm volatile("wgmma.commit_group.sync.aligned;" ::: "memory")
#define WG_WAIT(n) asm volatile("wgmma.wait_group.sync.aligned %0;" ::"n"(n) : "memory")
template <int N> __device__ __forceinline__ void reg_fence(float* d) {
#pragma unroll
    for (int i = 0; i < N; i++) asm volatile("" : "+f"(d[i])::"memory");
}
template <int N> __device__ __forceinline__ void reg_def(float* d) {
#pragma unroll
    for (int i = 0; i < N; i++) asm volatile("" : "=f"(d[i]));
}
template <int N> __device__ __forceinline__ void reg_def(uint32_t* d) {
#pragma unroll
    for (int i = 0; i < N; i++) asm volatile("" : "=r"(d[i]));
}
__device__ __forceinline__ bool is_unset(uint4 v) { return min(min(v.x, v.y), min(v.z, v.w)) == 0u; }
__device__ __forceinline__ uint4 nz4(uint32_t a, uint32_t b, uint32_t c, uint32_t d) { return make_uint4(max(a, 1u), max(b, 1u), max(c, 1u), max(d, 1u)); }
__device__ __forceinline__ void wait_flag(const uint32_t* p, uint32_t target) {
    int n = 0;
    while ((int)(ld_acquire(p) - target) < 0) { if (++n > SPIN_LIMIT) __trap(); }
}
__device__ __forceinline__ float silu_bf(uint32_t cbits) {
    float c = __uint_as_float(cbits << 16);
    return bf_round(c / (1.f + __expf(-c)));
}
__device__ __forceinline__ void fma8(float* acc, float s, uint4 w) {
    acc[0] += s * bf_lo(w.x); acc[1] += s * bf_hi(w.x); acc[2] += s * bf_lo(w.y); acc[3] += s * bf_hi(w.y);
    acc[4] += s * bf_lo(w.z); acc[5] += s * bf_hi(w.z); acc[6] += s * bf_lo(w.w); acc[7] += s * bf_hi(w.w);
}
__device__ __forceinline__ int unit_f(int u, int kh, int nq) {
    int sl, off; bool pa;
    if (u < 12) { sl = u >> 2; sl += sl >= nq; off = u & 3; pa = true; }
    else if (u < 16) { sl = nq; off = u - 12; pa = true; }
    else if (u < 19) { sl = nq; off = u - 16; pa = false; }
    else { const int v = u - 19; sl = v >= 6 ? 2 : v >= 3 ? 1 : 0; off = v - 3 * sl; sl += sl >= nq; pa = false; }
    const int ofs = 4 * kh + sl;
    return 224 * ofs + ((ofs & 1) ? (pa ? 96 : 0) : (pa ? 0 : 128)) + 32 * off;
}
__device__ __forceinline__ void ln_coeffs(float mean, float msq, uint32_t& r2, uint32_t& n2) {
    const float rs = bf_round(rsqrtf(fmaxf(msq - mean * mean, 0.f) + 1e-5f));
    r2 = pack2(rs, rs);
    n2 = pack2(-mean * rs, -mean * rs);
}

__global__ void __cluster_dims__(2, 1, 1) __launch_bounds__(384, 1) fused_block_kernel(const __grid_constant__ Params p) {
    extern __shared__ __align__(1024) unsigned char smem[];
    const uint32_t sb = (uint32_t)__cvta_generic_to_shared(smem);
    const int tid = threadIdx.x, lane = tid & 31, warp = __shfl_sync(~0u, tid >> 5, 0);
    const int m = blockIdx.x >> 1, kh = blockIdx.x & 1;
    int r, nq;
    {
        int g, i;
        if (m < MAP_S) { g = m < 4 ? 15 : 16; i = m & 3; }
        else if (m < MAP_S + 32) { g = (m - MAP_S) & 7; i = (m - MAP_S) >> 3; }
        else if (m < MAP_S + 60) { i = (m - MAP_S - 32) / 7; g = 8 + (m - MAP_S - 32) - 7 * i; }
        else { g = 16; i = m & 3; }
        r = g; nq = i;
    }
    const int j = 2 * nq + kh, b = 8 * r + j, fs = 4 * kh + nq;
    const uint32_t sc = r == 16;
#define BAR(i) (sb + M_BAR + 8 * (i))
    if (lane == 0 && warp < 9 && warp != 6 && warp != 7) {
        const int i0 = warp == 8 ? 0 : 8 + 8 * warp, cnt = warp >= 3 && warp < 8 ? 8 : 1;
#pragma unroll
        for (int k = 0; k < 8; k++) mbar_init(BAR(i0 + k), cnt);
        asm volatile("fence.mbarrier_init.release.cluster;" ::: "memory");
        fence_async_smem();
    }

    if (warp < 8) {
        const int w = warp >> 2, wi = warp & 3;
#define COORDS const int t = fresh_tid() & 127, lane = t & 31, q = lane & 3, lr = lane >> 2, ra = 64 * w + 16 * wi + lr; \
        const uint32_t lx = (lane >> 4) ^ (lane & 7), mrow = (64 * w + 16 * wi + ((lane >> 3) & 1) * 8 + (lane & 7)) * 128; \
        (void)q; (void)lr; (void)ra; (void)lx; (void)mrow;
#define XOFF ((lds1(sb + M_EPOCH) & 1) * XB + t)
        const int sid = 2 * (j & 3) + w;
#define RUN(k) (!sc || sid == (k))
#define WAIT(i, par) mbar_wait(BAR(i), (par) | sc)
        constexpr uint64_t DA128 = dconst(16, 1024, 1), DB128 = dconst(4096, 1024, 1);
        bar_sync(0, 384);
        asm volatile("barrier.cluster.arrive.relaxed.aligned;" ::: "memory");
        asm volatile("setmaxnreg.inc.sync.aligned.u32 224;");
        PROFC(0); PROFG(30);
        {
            COORDS
            uint32_t h[112];
            if (RUN(0)) {
                float ds[4] = {}, da[2][4] = {}, db[2][4] = {};
                const uint32_t ONE2 = 0x3F803F80u;
#pragma unroll
                for (int kb = 0; kb < 7; kb++) {
                    WAIT(B_XFULL + kb, 0);
#pragma unroll
                    for (int k4 = 0; k4 < 4; k4++) ldsm4(sb + OFF_X + mrow + kb * 16384 + (((2 * k4) ^ lx) << 4), h + 16 * kb + 4 * k4);
#pragma unroll
                    for (int k4 = 0; k4 < 4; k4++) {
                        const uint32_t* f = h + 16 * kb + 4 * k4;
                        mma16816(ds, f[0], f[1], f[2], f[3], ONE2, ONE2);
                        mma1688(da[0], f[0], f[1], f[0]); mma1688(db[0], f[0], f[1], f[1]);
                        mma1688(da[1], f[2], f[3], f[2]); mma1688(db[1], f[2], f[3], f[3]);
                    }
                }
                warp_arrive(BAR(B_XFREE));
                PROFC(27);
                float qa = (lr & 1) ? da[0][1] + da[1][1] : da[0][0] + da[1][0];
                float qb = (lr & 1) ? db[0][3] + db[1][3] : db[0][2] + db[1][2];
                const int src = (lane & ~3) | (lr >> 1);
                qa = __shfl_sync(~0u, qa, src);
                qb = __shfl_sync(~0u, qb, src);
                uint32_t ra2, na2, rb2, nb2;
                ln_coeffs(ds[0] * (1.f / DM), qa * (1.f / DM), ra2, na2);
                ln_coeffs(ds[2] * (1.f / DM), qb * (1.f / DM), rb2, nb2);
#pragma unroll
                for (int i = 0; i < 112; i += 2) { h[i] = hfma2(h[i], ra2, na2); h[i + 1] = hfma2(h[i + 1], rb2, nb2); }
            } else reg_def<112>(h);
            PROFC(1);
            if (RUN(1)) {
                float ak[28], av[28], aq[28];
                uint32_t kp[14], vp[14];
                const uint64_t bk0 = mkdesc(sb + OFF_Y, DB128), bv0 = mkdesc(sb + OFF_Y + HALF, DB128), bq0 = mkdesc(sb + OFF_X, DB128);
                uint32_t* kvg = g_kv + (size_t)(b * 2) * 3584 + (8 * w + 2 * wi) * 224 + lane;
                WAIT(B_FULLK, 0);
                WAIT(B_MOD1, 0);
                PROFC(2);
                reg_def<28>(ak);
#pragma unroll
                for (int g4 = 0; g4 < 4; g4++) {
#pragma unroll
                    for (int ks = 7 * g4; ks < 7 * g4 + 7; ks++) {
                        const uint4 st = *(const uint4*)(smem + M_ST + ks * 64 + q * 16);
                        h[4 * ks] = hfma2(h[4 * ks], st.x, st.y); h[4 * ks + 1] = hfma2(h[4 * ks + 1], st.x, st.y);
                        h[4 * ks + 2] = hfma2(h[4 * ks + 2], st.z, st.w); h[4 * ks + 3] = hfma2(h[4 * ks + 3], st.z, st.w);
                    }
                    WG_FENCE();
#pragma unroll
                    for (int ks = 7 * g4; ks < 7 * g4 + 7; ks++) wgmma_rs_56<1>(ak, h[4 * ks], h[4 * ks + 1], h[4 * ks + 2], h[4 * ks + 3], bk0 + ks * 128, ks != 0);
                }
                WG_COMMIT();
                PROFC(3);
                WAIT(B_FULLV, 0);
                reg_def<28>(av);
                WG_FENCE();
#pragma unroll
                for (int ks = 0; ks < 8; ks++) wgmma_rs_56<1>(av, h[4 * ks], h[4 * ks + 1], h[4 * ks + 2], h[4 * ks + 3], bv0 + ks * 128, ks != 0);
                WG_COMMIT();
                WG_WAIT(1);
                reg_fence<28>(ak);
                warp_arrive(BAR(B_KDONE));
#pragma unroll
                for (int g = 0; g < 7; g++) {
                    kp[2 * g] = pack2(ak[4 * g], ak[4 * g + 1]); kp[2 * g + 1] = pack2(ak[4 * g + 2], ak[4 * g + 3]);
                    kvg[g * 32] = kp[2 * g]; kvg[224 + g * 32] = kp[2 * g + 1];
                }
                warp_arrive(BAR(B_PUBK));
                PROFC(4);
                WG_FENCE();
#pragma unroll
                for (int ks = 8; ks < 28; ks++) wgmma_rs_56<1>(av, h[4 * ks], h[4 * ks + 1], h[4 * ks + 2], h[4 * ks + 3], bv0 + ks * 128, 1);
                WG_COMMIT();
                WAIT(B_FULLQ, 0);
                reg_def<28>(aq);
                WG_FENCE();
#pragma unroll
                for (int ks = 0; ks < 8; ks++) wgmma_rs_56<1>(aq, h[4 * ks], h[4 * ks + 1], h[4 * ks + 2], h[4 * ks + 3], bq0 + ks * 128, ks != 0);
                WG_COMMIT();
                WG_WAIT(1);
                reg_fence<28>(av);
#pragma unroll
                for (int g = 0; g < 7; g++) {
                    vp[2 * g] = pack2(av[4 * g], av[4 * g + 1]); vp[2 * g + 1] = pack2(av[4 * g + 2], av[4 * g + 3]);
                    kvg[3584 + g * 32] = vp[2 * g]; kvg[3584 + 224 + g * 32] = vp[2 * g + 1];
                }
                warp_arrive(BAR(B_PUBV));
                PROFC(5);
                WG_FENCE();
#pragma unroll
                for (int ks = 8; ks < 28; ks++) wgmma_rs_56<1>(aq, h[4 * ks], h[4 * ks + 1], h[4 * ks + 2], h[4 * ks + 3], bq0 + ks * 128, 1);
                WG_COMMIT();
                WAIT(B_PUBV, 0);
                const uint32_t ko = sb + OFF_Y + Y_KOWN + (8 * w + 2 * wi) * 896 + lane * 4;
                const uint32_t qo = sb + OFF_Y + Y_Q + (8 * w + 2 * wi) * 1024 + lane * 4;
#pragma unroll
                for (int g = 0; g < 7; g++) {
                    sts1(ko + g * 128, kp[2 * g]); sts1(ko + 896 + g * 128, kp[2 * g + 1]);
                    sts1(ko + (Y_VOWN - Y_KOWN) + g * 128, vp[2 * g]); sts1(ko + (Y_VOWN - Y_KOWN) + 896 + g * 128, vp[2 * g + 1]);
                }
                WG_WAIT(0);
                reg_fence<28>(aq);
                __syncwarp();
                if (lane < 3) mbar_arrive(BAR(B_EMPTY + lane));
#pragma unroll
                for (int g = 0; g < 7; g++) {
                    const uint32_t q0 = pack2(aq[4 * g], aq[4 * g + 1]), q1 = pack2(aq[4 * g + 2], aq[4 * g + 3]);
                    if (g == 3) {
                        sts1(qo + 3 * 128, q < 2 ? q0 : 0u); sts1(qo + 1024 + 3 * 128, q < 2 ? q1 : 0u);
                        sts1(qo + 4 * 128, q < 2 ? 0u : q0); sts1(qo + 1024 + 4 * 128, q < 2 ? 0u : q1);
                    } else {
                        const int ch = g < 3 ? g : g + 1;
                        sts1(qo + ch * 128, q0); sts1(qo + 1024 + ch * 128, q1);
                    }
                }
                fence_async_smem();
                if (!sc) bar_sync(3, 256);
            }
        }
        PROFC(6);
        WAIT(B_KRFULL, 0);
        PROFC(7);
        if (RUN(2) || RUN(3)) {
#pragma unroll 1
          for (int hf = sc; hf < 2; hf++) {
            float s[160];
            const float CS = 0.18898223650461361f * 1.4426950408889634f;
            float na = 0.f, nb = 0.f;
            {
                const uint64_t qd = mkdesc(sb + OFF_Y + Y_Q + hf * 8192 + w * 512, dconst(128, 1024, 0));
                const uint64_t kd = mkdesc(sb + OFF_Y + Y_K + hf * 8 * 896 + w * 384, dconst(128, 896, 0));
                reg_def<160>(s);
                WG_FENCE();
                wgmma_ss_160<0>(s, qd, kd, 0);
                wgmma_ss_160<0>(s, qd + 16, kd + 16, 1);
                wgmma_ss_160<0>(s + 80, qd, kd + 20 * 56, 0);
                wgmma_ss_160<0>(s + 80, qd + 16, kd + 20 * 56 + 16, 1);
                WG_COMMIT();
                WG_WAIT(0);
                reg_fence<160>(s);
            }
            if (RUN(2)) {
                COORDS
                const float NEG = __int_as_float(0xFF800000);
                if (r < 2) {
                    const int pmin = 4 - 2 * r - hf;
#pragma unroll
                    for (int p4 = 0; p4 < 4; p4++)
                        if (p4 < pmin) {
#pragma unroll
                            for (int i = 0; i < 32; i++) s[32 * p4 + i] = NEG;
                        }
                }
                float m0 = NEG, m1 = NEG, m2 = NEG, m3 = NEG;
                const bool c0 = 2 * q > lr, c1 = 2 * q + 1 > lr;
#pragma unroll
                for (int pp = 0; pp < 20; pp++) {
                    float* e = s + 8 * pp;
                    const bool act = pp < 3 ? pp >= wi : (pp > 16 ? pp <= wi + 16 : true);
                    if (act) {
                        if (pp < 4 && pp == wi) {
                            if (!c0) { e[0] = NEG; e[6] = NEG; }
                            if (!c1) { e[1] = NEG; e[7] = NEG; }
                            e[2] = NEG; e[3] = NEG;
                        }
                        if (pp >= 16 && pp == wi + 16) {
                            if (c0) { e[0] = NEG; e[6] = NEG; }
                            if (c1) { e[1] = NEG; e[7] = NEG; }
                            e[4] = NEG; e[5] = NEG;
                        }
                        m0 = fmaxf(m0, fmaxf(e[0], e[1])); m1 = fmaxf(m1, fmaxf(e[2], e[3]));
                        m2 = fmaxf(m2, fmaxf(e[4], e[5])); m3 = fmaxf(m3, fmaxf(e[6], e[7]));
                    }
                }
                float ma = fmaxf(m0, m2), mb = fmaxf(m1, m3);
                ma = fmaxf(ma, __shfl_xor_sync(~0u, ma, 1)); mb = fmaxf(mb, __shfl_xor_sync(~0u, mb, 1));
                ma = fmaxf(ma, __shfl_xor_sync(~0u, ma, 2)); mb = fmaxf(mb, __shfl_xor_sync(~0u, mb, 2));
                na = -ma * CS; nb = -mb * CS;
            }
            if (RUN(3)) {
                if (hf == 0) mbar_wait(BAR(B_VRFULL), 0);
                if (!sc && (w | hf)) bar_sync(4 + w, 256);
                PROFC(8 + 3 * hf);
                float o[16];
                float sa0 = 0.f, sa1 = 0.f, sb0 = 0.f, sb1 = 0.f;
                uint32_t P[80];
                const uint64_t vd = mkdesc(sb + OFF_Y + Y_VR + hf * 8 * 896 + w * 384, dconst(896, 128, 0));
                const uint64_t vd2 = vd + hf * ((Y_VOWN - 32 * 896) >> 4);
                reg_def<16>(o);
#pragma unroll
                for (int bt = 0; bt < 4; bt++) {
#pragma unroll
                    for (int pi = 0; pi < 5; pi++) {
                        const int pp = bt * 5 + pi;
                        float* e = s + 8 * pp;
                        const bool act = pp < 3 ? pp >= wi : (pp > 16 ? pp <= wi + 16 : true);
                        if (act) {
                            const float e0 = ex2(fmaf(e[0], CS, na)), e1 = ex2(fmaf(e[1], CS, na)), e2 = ex2(fmaf(e[2], CS, nb)), e3 = ex2(fmaf(e[3], CS, nb));
                            const float e4 = ex2(fmaf(e[4], CS, na)), e5 = ex2(fmaf(e[5], CS, na)), e6 = ex2(fmaf(e[6], CS, nb)), e7 = ex2(fmaf(e[7], CS, nb));
                            sa0 += e0 + e1; sb0 += e2 + e3; sa1 += e4 + e5; sb1 += e6 + e7;
                            P[4 * pp] = pack2(e0, e1); P[4 * pp + 1] = pack2(e2, e3); P[4 * pp + 2] = pack2(e4, e5); P[4 * pp + 3] = pack2(e6, e7);
                        } else {
                            P[4 * pp] = 0; P[4 * pp + 1] = 0; P[4 * pp + 2] = 0; P[4 * pp + 3] = 0;
                        }
                    }
                    if (bt == 3 && !sc && !(w & hf)) bar_arrive(5 - w, 256);
                    WG_FENCE();
#pragma unroll
                    for (int pi = 0; pi < 5; pi++) {
                        const int pp = bt * 5 + pi;
                        const uint64_t d = pp >= 16 ? vd + ((Y_VOWN - 32 * 896) >> 4) + pp * 112 : (pp >= 12 ? vd2 : vd) + pp * 112;
                        wgmma_rs_32<1>(o, P[4 * pp], P[4 * pp + 1], P[4 * pp + 2], P[4 * pp + 3], d, pp != 0);
                    }
                    WG_COMMIT();
                }
                PROFC(9 + 3 * hf);
                float sa = sa0 + sa1, sbb = sb0 + sb1;
                sa += __shfl_xor_sync(~0u, sa, 1); sbb += __shfl_xor_sync(~0u, sbb, 1);
                sa += __shfl_xor_sync(~0u, sa, 2); sbb += __shfl_xor_sync(~0u, sbb, 2);
                const float ia = __frcp_rn(sa), ib = __frcp_rn(sbb);
                WG_WAIT(0);
                reg_fence<16>(o);
                COORDS
                char* og = (char*)(g_o + (size_t)(2 * r + hf) * 32 * 128 + XOFF);
#pragma unroll
                for (int g = 0; g < 4; g++) {
                    const int G = 7 * j + 3 * w + g;
                    const bool on = (g == 3 - 3 * w) ? ((q >> 1) == w) : true;
                    if (on) st_relaxed2(og + (G >> 1) * 2048 + (G & 1) * 8, pack2(o[4 * g] * ia, o[4 * g + 1] * ia), pack2(o[4 * g + 2] * ib, o[4 * g + 3] * ib));
                }
                PROFC(10 + 3 * hf);
            }
          }
        }
        if (!sc) bar_arrive(6 + w, 256);
        uint32_t x1p[14];
        COORDS
        const int xoff = XOFF;
        if (RUN(4)) {
            uint32_t xr[14];
            const bf16* xg = p.x + (size_t)(128 * (r & 15) + ra) * DM + 56 * j + 2 * q;
#pragma unroll
            for (int g = 0; g < 7; g++) { xr[2 * g] = ldg_nc(xg + 8 * g); xr[2 * g + 1] = ldg_nc(xg + 8 * DM + 8 * g); }
            uint4 af[28];
            reg_def<112>((uint32_t*)af);
            const uint4* og = g_o + (size_t)(2 * r + w) * 32 * 128 + xoff;
            {
                const int G = 7 * ((lane & 15) >> 1) + 2 + 4 * (lane & 1);
                const char* pp = (const char*)og + (G >> 1) * 2048 + (G & 1) * 8;
                uint32_t done = 0;
#pragma unroll 1
                for (int n = 0; done != 0x1111u; n++) {
                    const uint2 v = ld_relaxed2(pp);
                    uint32_t ok = __ballot_sync(~0u, min(v.x, v.y) != 0u || sc);
                    ok &= ok >> 16; ok &= ok >> 2; ok &= ok >> 1; ok &= 0x1111u & ~done;
#pragma unroll
                    for (int u = 0; u < 4; u++)
                        if ((ok >> (4 * u)) & 1) {
#pragma unroll
                            for (int i = 7 * u; i < 7 * u + 7; i++) af[i] = ld_relaxed4(og + i * 128);
                        }
                    done |= ok;
                    if (n > SPIN_LIMIT) __trap();
                }
            }
            PROFC(28);
            WAIT(B_WOFULL, 0);
            float ac[28];
            const uint64_t bd = mkdesc(sb + OFF_X + HALF, DB128);
            reg_def<28>(ac);
#pragma unroll
            for (int u = 0; u < 4; u++) {
#pragma unroll 1
                for (int n = 0;; n++) {
                    uint32_t mn = ~0u;
#pragma unroll
                    for (int i = 7 * u; i < 7 * u + 7; i++) mn = min(mn, min(min(af[i].x, af[i].y), min(af[i].z, af[i].w)));
                    if (!__any_sync(~0u, mn == 0u) || sc) break;
#pragma unroll
                    for (int i = 7 * u; i < 7 * u + 7; i++) af[i] = ld_relaxed4(og + i * 128);
                    if (n > SPIN_LIMIT) __trap();
                }
                WG_FENCE();
#pragma unroll
                for (int i = 7 * u; i < 7 * u + 7; i++) wgmma_rs_56<1>(ac, af[i].x, af[i].y, af[i].z, af[i].w, bd + i * 128, i != 0);
                WG_COMMIT();
            }
            PROFC(14);
            WAIT(B_MOD2, 0);
            WG_WAIT(0);
            reg_fence<28>(ac);
            __syncwarp();
            if (lane < 4) mbar_arrive(BAR(B_EMPTY + 3 + lane));
            float s1a = 0.f, s2a = 0.f, s1b = 0.f, s2b = 0.f;
#pragma unroll
            for (int g = 0; g < 7; g++) {
                const float2 ga = *(const float2*)(smem + M_G + (8 * g + 2 * q) * 4);
                x1p[2 * g] = pack2(fmaf(ga.x, ac[4 * g], bf_lo(xr[2 * g])), fmaf(ga.y, ac[4 * g + 1], bf_hi(xr[2 * g])));
                x1p[2 * g + 1] = pack2(fmaf(ga.x, ac[4 * g + 2], bf_lo(xr[2 * g + 1])), fmaf(ga.y, ac[4 * g + 3], bf_hi(xr[2 * g + 1])));
                const float u0 = bf_lo(x1p[2 * g]), u1 = bf_hi(x1p[2 * g]), u2 = bf_lo(x1p[2 * g + 1]), u3 = bf_hi(x1p[2 * g + 1]);
                s1a += u0 + u1; s2a += u0 * u0 + u1 * u1; s1b += u2 + u3; s2b += u2 * u2 + u3 * u3;
            }
            uint4* xo = g_x1 + (size_t)(((2 * r + w) * 8 + j) * 4) * 128 + xoff;
            st_relaxed4(xo, nz4(x1p[0], x1p[1], x1p[2], x1p[3]));
            st_relaxed4(xo + 128, nz4(x1p[4], x1p[5], x1p[6], x1p[7]));
            st_relaxed4(xo + 256, nz4(x1p[8], x1p[9], x1p[10], x1p[11]));
            float ka = (q & 1) ? s2a : s1a, kb2 = (q & 1) ? s2b : s1b;
            ka += __shfl_xor_sync(~0u, (q & 1) ? s1a : s2a, 1); kb2 += __shfl_xor_sync(~0u, (q & 1) ? s1b : s2b, 1);
            ka += __shfl_xor_sync(~0u, ka, 2); kb2 += __shfl_xor_sync(~0u, kb2, 2);
            st_relaxed4(xo + 384, nz4(x1p[12], x1p[13], __float_as_uint(ka), __float_as_uint(kb2)));
        } else reg_def<14>(x1p);
        PROFC(15);
        if (RUN(5)) {
            uint4 xf[32];
            reg_def<128>((uint32_t*)xf);
            const uint4* xg = g_x1 + (size_t)((2 * r + w) * 32) * 128 + xoff;
            const uint4* pp = xg + (4 * (lane & 7) + 3) * 128;
            uint32_t done = 0;
#pragma unroll 1
            for (int n = 0;; n++) {
                uint32_t ok = __ballot_sync(~0u, !is_unset(ld_relaxed4(pp)) || sc);
                ok &= ok >> 16; ok &= ok >> 8; ok &= 0xFFu & ~done;
#pragma unroll
                for (int u = 0; u < 8; u++)
                    if ((ok >> u) & 1) {
#pragma unroll
                        for (int i = 4 * u; i < 4 * u + 4; i++) xf[i] = ld_relaxed4(xg + i * 128);
                    }
                done |= ok;
                if (done == 0xFFu) {
                    PROFC(16);
                    uint32_t mn = ~0u;
#pragma unroll
                    for (int i = 0; i < 32; i++) mn = min(mn, min(min(xf[i].x, xf[i].y), min(xf[i].z, xf[i].w)));
                    if (!__any_sync(~0u, mn == 0u) || sc) break;
                    done = 0;
                }
                if (n > SPIN_LIMIT) __trap();
            }
            PROFC(29);
            float ka = 0.f, kb2 = 0.f;
#pragma unroll
            for (int jj = 0; jj < 8; jj++) { ka += __uint_as_float(xf[4 * jj + 3].z); kb2 += __uint_as_float(xf[4 * jj + 3].w); }
            const float oa = __shfl_xor_sync(~0u, ka, 1), ob = __shfl_xor_sync(~0u, kb2, 1);
            uint32_t ra2, na2, rb2, nb2;
            ln_coeffs(((q & 1) ? oa : ka) * (1.f / DM), ((q & 1) ? ka : oa) * (1.f / DM), ra2, na2);
            ln_coeffs(((q & 1) ? ob : kb2) * (1.f / DM), ((q & 1) ? kb2 : ob) * (1.f / DM), rb2, nb2);
            uint32_t* xw = (uint32_t*)xf;
            if (!sc) bar_sync(7 - w, 256);
#pragma unroll
            for (int G8 = 0; G8 < 56; G8 += 8) {
#pragma unroll
                for (int G = G8; G < G8 + 8; G += 2) {
                    const uint4 st = *(const uint4*)(smem + M_ST + (G >> 1) * 64 + q * 16);
                    const int i0 = (G / 7) * 16 + (G % 7) * 2, i1 = ((G + 1) / 7) * 16 + ((G + 1) % 7) * 2;
                    xw[i0] = hfma2(hfma2(xw[i0], ra2, na2), st.x, st.y); xw[i0 + 1] = hfma2(hfma2(xw[i0 + 1], rb2, nb2), st.x, st.y);
                    xw[i1] = hfma2(hfma2(xw[i1], ra2, na2), st.z, st.w); xw[i1 + 1] = hfma2(hfma2(xw[i1 + 1], rb2, nb2), st.z, st.w);
                }
#pragma unroll
                for (int G = G8; G < G8 + 8; G += 2) {
                    const int i0 = (G / 7) * 16 + (G % 7) * 2, i1 = ((G + 1) / 7) * 16 + ((G + 1) % 7) * 2;
                    stsm4(sb + OFF_Y + mrow + (G >> 3) * 16384 + (((G & 7) ^ lx) << 4), xw[i0], xw[i0 + 1], xw[i1], xw[i1 + 1]);
                }
            }
            fence_async_smem();
            bar_sync(1 + w, 128);
        }
        PROFC(17);
        uint32_t h2a[32], h2b[24];
        if (RUN(6)) {
            const int fa = 224 * fs + ((fs & 1) ? 96 : 0), fb = 224 * fs + ((fs & 1) ? 0 : 128);
            uint32_t* h2g = g_h2 + (size_t)r * (224 * 512) + (8 * w + 2 * wi) * 32 + lane;
            const uint64_t a0 = mkdesc(sb + OFF_Y + w * 8192, DA128);
            const int s0 = sc ? 12 : 0;
            {
                float ac[128];
                reg_def<128>(ac);
                int sl = 0, prev = 0;
#pragma unroll 1
                for (int s = s0; s < 14; s++) {
                    WAIT(B_FULL + sl, s >= 7);
                    const uint64_t ad = a0 + (s >> 1) * 1024 + (s & 1) * 4, bd = mkdesc(sb + OFF_X + sl * 16384, DB128);
                    WG_FENCE();
                    wgmma_ss_256<1>(ac, ad, bd, s != 0);
                    wgmma_ss_256<1>(ac, ad + 2, bd + 128, 1);
                    WG_COMMIT();
                    if (s > 0) { WG_WAIT(1); warp_arrive(BAR(B_EMPTY + prev)); }
                    prev = sl; sl = sl == 6 ? 0 : sl + 1;
                }
                WG_WAIT(0);
                reg_fence<128>(ac);
                warp_arrive(BAR(B_EMPTY + 6));
                PROFC(18);
#pragma unroll
                for (int g = 0; g < 16; g++) {
                    h2a[2 * g] = hmul2(pack2_relu(ac[4 * g], ac[4 * g + 1]), pack2(ac[64 + 4 * g], ac[64 + 4 * g + 1]));
                    h2a[2 * g + 1] = hmul2(pack2_relu(ac[4 * g + 2], ac[4 * g + 3]), pack2(ac[64 + 4 * g + 2], ac[64 + 4 * g + 3]));
                    h2g[(fa / 8 + g) * 512] = h2a[2 * g]; h2g[(fa / 8 + g) * 512 + 32] = h2a[2 * g + 1];
                }
                warp_arrive(BAR(B_PUBA));
            }
            PROFC(19);
            {
                float ac[96];
                reg_def<96>(ac);
                int sl = 0, prev = 0;
#pragma unroll 1
                for (int s = s0; s < 14; s++) {
                    WAIT(B_FULL + sl, s >= 7);
                    const uint64_t ad = a0 + (s >> 1) * 1024 + (s & 1) * 4, bd = mkdesc(sb + OFF_X + sl * 16384, dconst(2048, 512, 2));
                    WG_FENCE();
                    wgmma_ss_192<1>(ac, ad, bd, s != 0);
                    wgmma_ss_192<1>(ac, ad + 2, bd + 64, 1);
                    WG_COMMIT();
                    if (s > 0) { WG_WAIT(1); warp_arrive(BAR(B_EMPTY + prev)); }
                    prev = sl; sl = sl == 6 ? 0 : sl + 1;
                }
                WG_WAIT(0);
                reg_fence<96>(ac);
                __syncwarp();
                if (lane < 6) mbar_arrive(BAR(B_EMPTY + 6 + lane));
                asm volatile("barrier.cluster.wait.aligned;" ::: "memory");
                if (lane == 0 && !sc) {
                    uint32_t rb;
                    asm volatile("mapa.shared::cluster.u32 %0, %1, %2;" : "=r"(rb) : "r"(BAR(B_PEER)), "r"(kh ^ 1));
                    asm volatile("mbarrier.arrive.relaxed.cluster.shared::cluster.b64 _, [%0];" ::"r"(rb) : "memory");
                }
                PROFC(20);
#pragma unroll
                for (int g = 0; g < 12; g++) {
                    h2b[2 * g] = hmul2(pack2_relu(ac[4 * g], ac[4 * g + 1]), pack2(ac[48 + 4 * g], ac[48 + 4 * g + 1]));
                    h2b[2 * g + 1] = hmul2(pack2_relu(ac[4 * g + 2], ac[4 * g + 3]), pack2(ac[48 + 4 * g + 2], ac[48 + 4 * g + 3]));
                    h2g[(fb / 8 + g) * 512] = h2b[2 * g]; h2g[(fb / 8 + g) * 512 + 32] = h2b[2 * g + 1];
                }
                warp_arrive(BAR(B_PUBB));
            }
        } else { reg_def<32>(h2a); reg_def<24>(h2b); }
        PROFC(21);
        if (RUN(7)) {
            float ac[56];
            reg_def<56>(ac);
            constexpr uint64_t DAN = dconst(2048, 128, 0);
#pragma unroll 1
            for (int u = 0; u < 12; u++) {
                WAIT(B_FULL + u, 0);
                const uint32_t sl = sb + u * 16384;
                const uint64_t ad = mkdesc(sl + 8192 + w * 1024, DAN), bd = mkdesc(sl, DB128);
                WG_FENCE();
                wgmma_ss_112<1>(ac, ad, bd, u != 0);
                wgmma_ss_112<1>(ac, ad + 256, bd + 128, 1);
                WG_COMMIT();
                if (u > 0) { WG_WAIT(1); warp_arrive(BAR(B_EMPTY + u - 1)); }
            }
            PROFC(22);
#pragma unroll
            for (int u = 0; u < 7; u++) {
                WAIT(B_FULL + u, 1);
                const uint64_t bd = mkdesc(sb + u * 16384, DB128);
                const uint32_t* hh = u < 4 ? h2a + 8 * u : h2b + 8 * (u - 4);
                WG_FENCE();
                wgmma_rs_112<1>(ac, hh[0], hh[1], hh[2], hh[3], bd, 1);
                wgmma_rs_112<1>(ac, hh[4], hh[5], hh[6], hh[7], bd + 128, 1);
                WG_COMMIT();
                if (u > 0 && u < 5) { WG_WAIT(1); warp_arrive(BAR(B_EMPTY + u - 1)); }
                if (u == 0) { WG_WAIT(1); warp_arrive(BAR(B_EMPTY + 11)); }
            }
            PROFC(23);
#pragma unroll 1
            for (int u = 7; u < 16; u++) {
                const int sli = u < 12 ? u : u - 12;
                WAIT(B_FULL + sli, u < 12);
                const uint32_t sl = sb + sli * 16384;
                const uint64_t ad = mkdesc(sl + 8192 + w * 1024, DAN), bd = mkdesc(sl, DB128);
                WG_FENCE();
                wgmma_ss_112<1>(ac, ad, bd, 1);
                wgmma_ss_112<1>(ac, ad + 256, bd + 128, 1);
                WG_COMMIT();
            }
            mbar_wait_cluster(BAR(B_PEER), sc);
            WG_WAIT(0);
            reg_fence<56>(ac);
            PROFC(24);
            uint32_t rdst, rbar;
            asm volatile("mapa.shared::cluster.u32 %0, %1, %2;" : "=r"(rdst) : "r"(sb + OFF_Y + (5 + w) * 16384 + t * 16), "r"(kh ^ 1 ^ sc));
            asm volatile("mapa.shared::cluster.u32 %0, %1, %2;" : "=r"(rbar) : "r"(BAR(B_XCH + w)), "r"(kh ^ 1 ^ sc));
#pragma unroll
            for (int g = 0; g < 7; g++) {
                const float v0 = kh ? ac[4 * g] : ac[28 + 4 * g], v1 = kh ? ac[4 * g + 1] : ac[28 + 4 * g + 1];
                const float v2 = kh ? ac[4 * g + 2] : ac[28 + 4 * g + 2], v3 = kh ? ac[4 * g + 3] : ac[28 + 4 * g + 3];
                if (!sc) asm volatile("st.async.shared::cluster.mbarrier::complete_tx::bytes.v4.f32 [%0], {%1,%2,%3,%4}, [%5];"
                             ::"r"(rdst + g * 2048), "f"(v0), "f"(v1), "f"(v2), "f"(v3), "r"(rbar) : "memory");
            }
            mbar_wait_cluster(BAR(B_XCH + w), sc);
            PROFC(25);
            bf16* og = (sc ? (bf16*)(g_h2 + 16 * 224 * 512) : p.out + (size_t)128 * r * DM) + (size_t)ra * DM + 56 * j + 2 * q;
#pragma unroll
            for (int g = 0; g < 7; g++) {
                const uint4 rv = *(const uint4*)(smem + OFF_Y + (5 + w) * 16384 + t * 16 + g * 2048);
                const float2 gb = *(const float2*)(smem + M_G + 224 + (8 * g + 2 * q) * 4);
                const float v0 = (kh ? ac[28 + 4 * g] : ac[4 * g]) + __uint_as_float(rv.x), v1 = (kh ? ac[28 + 4 * g + 1] : ac[4 * g + 1]) + __uint_as_float(rv.y);
                const float v2 = (kh ? ac[28 + 4 * g + 2] : ac[4 * g + 2]) + __uint_as_float(rv.z), v3 = (kh ? ac[28 + 4 * g + 3] : ac[4 * g + 3]) + __uint_as_float(rv.w);
                *(uint32_t*)(og + 8 * g) = pack2(fmaf(gb.x, v0, bf_lo(x1p[2 * g])), fmaf(gb.y, v1, bf_hi(x1p[2 * g])));
                *(uint32_t*)(og + 8 * DM + 8 * g) = pack2(fmaf(gb.x, v2, bf_lo(x1p[2 * g + 1])), fmaf(gb.y, v3, bf_hi(x1p[2 * g + 1])));
            }
        }
        PROFC(26); PROFG(31);
        warp_arrive(BAR(B_DONE));
    } else {
        const int tl = tid - 288;
        const bool early = kh == 0, gemv = r < 14;
        const int mcol = early ? 16 * (4 * r + nq) : 2 * DM + 32 * (4 * r + nq);
        const uint32_t wmbuf = sb + (early ? OFF_Y + HALF + 5 * 8192 : OFF_X + HALF);
        uint32_t ticket = 0;
        if (!sc) {
            if (tid == 256) {
#pragma unroll 1
                for (int kb = 0; kb < 7; kb++) {
                    mbar_expect_tx(BAR(B_XFULL + kb), 16384);
                    tma3(sb + OFF_X + kb * 16384, &p.xm, 64 * kb, 128 * r, 0, BAR(B_XFULL + kb));
                }
            }
            if (tl == 32) ticket = atomicAdd(&g_ticket, 1u);
        }
        if (tl == 0) {
            mbar_init(BAR(B_WMFULL), 1);
            fence_async_smem();
            if (early && gemv) {
                mbar_expect_tx(BAR(B_WMFULL), 14336);
#pragma unroll 1
                for (int k = 0; k < WMB; k++) tma3(wmbuf + k * (14336 / WMB), &p.wm, mcol, k * (DM / WMB), 0, BAR(B_WMFULL));
            }
            mbar_init(BAR(B_MOD1), 3); mbar_init(BAR(B_MOD2), 3); mbar_init(BAR(B_WMFREE), 3);
        }
        bar_sync(0, 384);
        asm volatile("barrier.cluster.arrive.relaxed.aligned;" ::: "memory");
        asm volatile("setmaxnreg.dec.sync.aligned.u32 56;");
        if (sc) return;
        if (warp == 8) {
            if (lane == 0) {
                const int fa = 224 * fs + ((fs & 1) ? 96 : 0), fb = 224 * fs + ((fs & 1) ? 0 : 128);
                PROF(2, 0);
#pragma unroll 1
                for (int mt = 0; mt < 4; mt++) {
                    if (mt == 1) mbar_wait(BAR(B_XFULL + 6), 0);
                    if (mt == 2) mbar_wait(BAR(B_XFREE), 0);
                    if (mt == 3) {
                        if (!early && gemv) {
                            mbar_expect_tx(BAR(B_WMFULL), 28672);
#pragma unroll 1
                            for (int k = 0; k < 2 * WMB; k++) tma3(wmbuf + k * (14336 / WMB), &p.wm, mcol + (k >= WMB ? 16 : 0), (k >= WMB ? k - WMB : k) * (DM / WMB), 0, BAR(B_WMFULL));
                        }
                        mbar_wait(BAR(B_WMFREE), 0); mbar_wait(BAR(B_VRFULL), 0);
                    }
                    const uint32_t bar = BAR(mt == 3 ? B_WOFULL : B_FULLK + mt), dst = sb + (mt < 2 ? OFF_Y : OFF_X) + (mt & 1) * HALF;
                    const int c1 = (mt < 2 ? 8 + 8 * mt : 0) + j;
                    mbar_expect_tx(bar, HALF);
#pragma unroll 1
                    for (int kb = 0; kb < 7; kb++) {
                        if (mt == 1 && kb == 5 && early) mbar_wait(BAR(B_WMFREE), 0);
                        tma3(dst + kb * 8192, mt == 3 ? &p.wo : &p.qkv, 0, c1, 64 * kb, bar);
                    }
                    PROF(2, 5 + mt);
                }
                mbar_expect_tx(BAR(B_XCH), 14336);
                mbar_expect_tx(BAR(B_XCH + 1), 14336);
                int sl = 0;
#pragma unroll 1
                for (int s = 0; s < 28; s++) {
                    mbar_wait(BAR(B_EMPTY + sl), (s >= 7 && s < 14) || s >= 21);
                    const uint32_t dst = sb + OFF_X + sl * 16384;
                    const bool pa = s < 14;
                    mbar_expect_tx(BAR(B_FULL + sl), pa ? 16384 : 12288);
                    const int k0 = 32 * (pa ? s : s - 14), c2 = pa ? fa >> 6 : fb >> 5;
                    tma3(dst, pa ? &p.ga : &p.gb, 0, k0, c2, BAR(B_FULL + sl));
                    tma3(dst + (pa ? 8192 : 6144), pa ? &p.ua : &p.ub, 0, k0, c2, BAR(B_FULL + sl));
                    sl = sl == 6 ? 0 : sl + 1;
                }
                PROF(2, 3);
                sl = 0;
#pragma unroll 1
                for (int u = 0; u < 28; u++) {
                    const int f = unit_f(u, kh, nq);
                    mbar_wait(BAR(B_EMPTY + sl), u >= 12 && u < 24);
                    const uint32_t dst = sb + sl * 16384;
                    mbar_expect_tx(BAR(B_FULL + sl), (u < 12 || u >= 19) ? 16384 : 8192);
                    tma3(dst, &p.dn, 0, nq, f, BAR(B_FULL + sl));
                    tma3(dst + 4096, &p.dn, 64, nq, f, BAR(B_FULL + sl));
                    if (u == 0 || u == 19) { mbar_wait(BAR(B_HRDY + (u != 0)), 0); fence_async_global(); }
                    if (u < 12 || u >= 19) bulk_load(dst + 8192, g_h2 + (size_t)r * (224 * 512) + (size_t)(f >> 3) * 512, 8192, BAR(B_FULL + sl));
                    sl = sl == 11 ? 0 : sl + 1;
                }
                PROF(2, 4);
                mbar_wait(BAR(B_DONE), 0);
            }
            return;
        }
        float cs[5];
#pragma unroll
        for (int i = 0; i < 5; i++) cs[i] = (tl + 96 * i < DM) ? silu_bf(__ldg((const unsigned short*)p.c + min(tl + 96 * i, DM - 1))) : 0.f;
        if (tl == 32) sts1(sb + M_EPOCH, ticket / NCTA);
        bar_sync(8, 96);
        const uint32_t target = lds1(sb + M_EPOCH) + 1, tag = target & 0xFFFFu;
        const uint4* modp = (const uint4*)g_mod + (r & 7) * (6 * DM / 4);
#pragma unroll 1
        for (int step = 0; step < 5; step++) {
            if (step >= 2 && warp != 11) break;
            if (step < 2 && (step == 0) == early) {
                if (gemv) {
                    mbar_wait(BAR(B_WMFULL), 0);
                    PROF(3, 9);
#pragma unroll 1
                    for (int pn = 0; pn < (early ? 1 : 2); pn++) {
                        float a0[8] = {}, a1[8] = {};
#pragma unroll
                        for (int i = 0; i < 5; i++) {
                            const uint32_t a = wmbuf + pn * 14336 + min(tl + 96 * i, DM - 1) * 32;
                            fma8(a0, cs[i], lds4(a + ((lane & 4) << 2)));
                            fma8(a1, cs[i], lds4(a + 16 - ((lane & 4) << 2)));
                        }
#pragma unroll
                        for (int i = 0; i < 8; i++) a0[i] += __shfl_xor_sync(~0u, a1[i], 4);
                        bool hh = lane & 16;
#pragma unroll
                        for (int i = 0; i < 4; i++) { const float snd = hh ? a0[i] : a0[i + 4], kp = hh ? a0[i + 4] : a0[i]; a0[i] = kp + __shfl_xor_sync(~0u, snd, 16); }
                        hh = lane & 8;
#pragma unroll
                        for (int i = 0; i < 2; i++) { const float snd = hh ? a0[i] : a0[i + 2], kp = hh ? a0[i + 2] : a0[i]; a0[i] = kp + __shfl_xor_sync(~0u, snd, 8); }
                        hh = lane & 2;
                        float v = (hh ? a0[1] : a0[0]) + __shfl_xor_sync(~0u, hh ? a0[0] : a0[1], 2);
                        v += __shfl_xor_sync(~0u, v, 1);
                        const int col = ((lane & 4) << 1) | ((lane & 16) >> 2) | ((lane & 8) >> 2) | ((lane & 2) >> 1);
                        if (!(lane & 1)) sts1(sb + M_RED + ((warp - 9) * 16 + col) * 4, __float_as_uint(v));
                        bar_sync(8, 96);
                        const int c16 = tl & 15;
                        const float sum = __uint_as_float(lds1(sb + M_RED + c16 * 4)) + __uint_as_float(lds1(sb + M_RED + 64 + c16 * 4)) + __uint_as_float(lds1(sb + M_RED + 128 + c16 * 4));
                        const uint32_t word = (pack2(sum, 0.f) << 16) | tag;
                        if (tl < 64) {
                            st_relaxed(&g_mod[(tl >> 4) * (6 * DM) + mcol + 16 * pn + c16], word);
                            st_relaxed(&g_mod[((tl >> 4) + 4) * (6 * DM) + mcol + 16 * pn + c16], word);
                        }
                        if (!early) bar_sync(8, 96);
                    }
                    PROF(3, 0);
                }
                warp_arrive(BAR(B_WMFREE));
            } else {
                const bool p2 = step >= 2;
                const int i0 = p2 ? lane + 32 * (step - 2) : tl, imax = p2 ? 251 : 223;
                mbar_wait(BAR(p2 ? B_PUBV : B_XFULL + 6), 0);
                uint4 v[3];
#pragma unroll 1
                for (int n = 0;; n++) {
                    uint32_t bad = 0;
#pragma unroll
                    for (int k = 0; k < 3; k++) {
                        const int i = min(i0 + 96 * k, imax);
                        v[k] = ld_relaxed4(modp + (i < 224 ? (p2 ? 336 : 0) + i : (i < 238 ? 14 * j + i : 14 * j + i + 322)));
                        bad |= (v[k].x ^ tag) | (v[k].y ^ tag) | (v[k].z ^ tag) | (v[k].w ^ tag);
                    }
                    if (!(bad & 0xFFFFu)) break;
                    if (n > SPIN_LIMIT) __trap();
                }
#pragma unroll
                for (int k = 0; k < 3; k++) {
                    const int i = min(i0 + 96 * k, imax);
                    if (i < 224) {
                        const int isc = i >= 112, c4 = i - 112 * isc;
                        const float one = isc ? 1.f : 0.f;
                        const uint32_t a = sb + M_ST + (c4 >> 2) * 64 + (c4 & 1) * 32 + (c4 & 2) * 4 + (isc ? 0 : 4);
                        sts1(a, pack2(bf_hi(v[k].x) + one, bf_hi(v[k].y) + one));
                        sts1(a + 16, pack2(bf_hi(v[k].z) + one, bf_hi(v[k].w) + one));
                    } else {
                        sts4(sb + M_G + (i - 224) * 16, make_uint4(v[k].x & 0xFFFF0000u, v[k].y & 0xFFFF0000u, v[k].z & 0xFFFF0000u, v[k].w & 0xFFFF0000u));
                    }
                }
                warp_arrive(BAR(p2 ? B_MOD2 : B_MOD1));
                PROF(3, p2 ? 5 : 1);
                if (tl == 64 && !p2) {
                    l2_prefetch((const char*)p.wop + (size_t)b * 3136, 3136);
                    l2_prefetch((const char*)p.wg + (size_t)b * 12544, 12544);
                    l2_prefetch((const char*)p.wu + (size_t)b * 12544, 12544);
                    l2_prefetch((const char*)p.wd + (size_t)b * 12544, 12544);
                }
            }
        }
        if (warp == 9) {
#pragma unroll 1
            for (int kv = 0; kv < 2; kv++) {
                mbar_wait(BAR(B_PUBK + kv), 0);
                if (lane >= 1 && lane <= 2 && r >= lane) wait_flag((kv ? g_flagV : g_flagK) + (b - 8 * lane) * 8, target);
                __syncwarp();
                PROF(3, 8);
                if (lane == 0) {
                    fence_async_global();
                    mbar_wait(BAR(B_KDONE), 0);
                    const uint32_t dst = sb + OFF_Y + (kv ? Y_VR : Y_K);
                    mbar_expect_tx(BAR(B_KRFULL + kv), r >= 2 ? 28672 : r == 1 ? 14336 : 0);
                    if (r >= 2) bulk_load(dst, g_kv + (size_t)((b - 16) * 2 + kv) * 3584, 14336, BAR(B_KRFULL + kv));
                    if (r >= 1) bulk_load(dst + 14336, g_kv + (size_t)((b - 8) * 2 + kv) * 3584, 14336, BAR(B_KRFULL + kv));
                }
                PROF(3, 2 + kv);
            }
#pragma unroll 1
            for (int ps = 0; ps < 2; ps++) {
                mbar_wait(BAR(B_PUBA + ps), 0);
                if (lane < 4) wait_flag(&g_flagH[((r * 8 + 4 * kh + lane) * 2 + ps) * 8], target);
                warp_arrive(BAR(B_HRDY + ps));
                PROF(3, 6 + ps);
            }
        } else if (warp == 10) {
            if (lane == 0) {
#pragma unroll 1
                for (int k = 0; k < 4; k++) {
                    mbar_wait(BAR(B_PUBK + k), 0);
                    if (k == 0) PROF(3, 10);
                    fence_gpu();
                    st_relaxed(k == 0 ? &g_flagK[b * 8] : k == 1 ? &g_flagV[b * 8] : &g_flagH[((r * 8 + fs) * 2 + k - 2) * 8], target);
                    if (k == 0) PROF(3, 11);
                }
            }
        } else {
            mbar_wait(BAR(B_VRFULL), 0);
            const int idle = (target & 1) * XB + (2 * r * 32 + 4 * j) * 128;
#pragma unroll 4
            for (int i = lane; i < 1024; i += 32) {
                const int k = idle + (i >> 9) * 4096 + (i & 511);
                g_o[k] = make_uint4(0, 0, 0, 0);
                g_x1[k] = make_uint4(0, 0, 0, 0);
            }
        }
    }
}

typedef CUresult (*EncodeFn)(CUtensorMap*, CUtensorMapDataType, cuuint32_t, void*, const cuuint64_t*, const cuuint64_t*, const cuuint32_t*,
                             const cuuint32_t*, CUtensorMapInterleave, CUtensorMapSwizzle, CUtensorMapL2promotion, CUtensorMapFloatOOBfill);

static void make_map(EncodeFn fn, CUtensorMap* m, const void* ptr, uint64_t d0, uint64_t d1, uint64_t d2, uint64_t s1, uint64_t s2,
                     uint32_t b0, uint32_t b1, uint32_t b2, CUtensorMapSwizzle sw) {
    cuuint64_t dims[3] = {d0, d1, d2}, strides[2] = {s1, s2};
    cuuint32_t box[3] = {b0, b1, b2}, es[3] = {1, 1, 1};
    CUresult rc = fn(m, CU_TENSOR_MAP_DATA_TYPE_BFLOAT16, 3, (void*)ptr, dims, strides, box, es, CU_TENSOR_MAP_INTERLEAVE_NONE, sw,
                     CU_TENSOR_MAP_L2_PROMOTION_L2_128B, CU_TENSOR_MAP_FLOAT_OOB_FILL_NONE);
    (void)rc;
}

extern "C" void kernel_launch(void* const* d_in, const int* in_sizes, int n_in, void* d_out, int out_size) {
    (void)in_sizes; (void)n_in; (void)out_size;
    static EncodeFn fn = nullptr;
    if (!fn) {
        cudaDriverEntryPointQueryResult st;
        cudaGetDriverEntryPoint("cuTensorMapEncodeTiled", (void**)&fn, cudaEnableDefault, &st);
        cudaFuncSetAttribute(fused_block_kernel, cudaFuncAttributeMaxDynamicSharedMemorySize, SMEM_BYTES);
    }
    Params p;
    p.x = (const bf16*)d_in[0];
    const bf16* wqkv = (const bf16*)d_in[1];
    p.wop = (const bf16*)d_in[2];
    p.wg = (const bf16*)d_in[4];
    p.wu = (const bf16*)d_in[5];
    p.wd = (const bf16*)d_in[6];
    p.c = (const bf16*)d_in[7];
    p.wmod = (const bf16*)d_in[8];
    p.out = (bf16*)d_out;
    make_map(fn, &p.wm, p.wmod, 2688, 448, 1, 5376, 5376 * 448, 16, DM / WMB, 1, CU_TENSOR_MAP_SWIZZLE_NONE);
    make_map(fn, &p.xm, p.x, 448, 2048, 1, 896, 896 * 2048, 64, 128, 1, CU_TENSOR_MAP_SWIZZLE_128B);
    make_map(fn, &p.qkv, wqkv, 56, 24, 448, 112, 2688, 64, 1, 64, CU_TENSOR_MAP_SWIZZLE_128B);
    make_map(fn, &p.wo, p.wop, 56, 8, 448, 112, 896, 64, 1, 64, CU_TENSOR_MAP_SWIZZLE_128B);
    make_map(fn, &p.ga, p.wg, 64, 448, 28, 3584, 128, 64, 32, 2, CU_TENSOR_MAP_SWIZZLE_128B);
    make_map(fn, &p.ua, p.wu, 64, 448, 28, 3584, 128, 64, 32, 2, CU_TENSOR_MAP_SWIZZLE_128B);
    make_map(fn, &p.gb, p.wg, 32, 448, 56, 3584, 64, 32, 32, 3, CU_TENSOR_MAP_SWIZZLE_64B);
    make_map(fn, &p.ub, p.wu, 32, 448, 56, 3584, 64, 32, 32, 3, CU_TENSOR_MAP_SWIZZLE_64B);
    make_map(fn, &p.dn, p.wd, 112, 4, 1792, 224, 896, 64, 1, 32, CU_TENSOR_MAP_SWIZZLE_128B);
    fused_block_kernel<<<GRID, 384, SMEM_BYTES>>>(p);
}
```

```cpp
#include <cuda_runtime.h>
#include <cuda_bf16.h>
#include <cuda.h>
#include <stdint.h>

typedef __nv_bfloat16 bf16;

template<int TB> __device__ __forceinline__ void wgmma_rs_56(float* d, uint32_t a0, uint32_t a1, uint32_t a2, uint32_t a3, uint64_t db, int sd) {
  asm volatile("{\n.reg .pred p;\nsetp.ne.b32 p, %33, 0;\n"
    "wgmma.mma_async.sync.aligned.m64n56k16.f32.bf16.bf16 {%0,%1,%2,%3,%4,%5,%6,%7,%8,%9,%10,%11,%12,%13,%14,%15,%16,%17,%18,%19,%20,%21,%22,%23,%24,%25,%26,%27}, {%28,%29,%30,%31}, %32, p, 1, 1, %34;\n}\n"
    : "+f"(d[0]),"+f"(d[1]),"+f"(d[2]),"+f"(d[3]),"+f"(d[4]),"+f"(d[5]),"+f"(d[6]),"+f"(d[7]),"+f"(d[8]),"+f"(d[9]),"+f"(d[10]),"+f"(d[11]),"+f"(d[12]),"+f"(d[13]),"+f"(d[14]),"+f"(d[15]),"+f"(d[16]),"+f"(d[17]),"+f"(d[18]),"+f"(d[19]),"+f"(d[20]),"+f"(d[21]),"+f"(d[22]),"+f"(d[23]),"+f"(d[24]),"+f"(d[25]),"+f"(d[26]),"+f"(d[27])
    : "r"(a0), "r"(a1), "r"(a2), "r"(a3), "l"(db), "r"(sd), "n"(TB));
}
template<int TB> __device__ __forceinline__ void wgmma_ss_256(float* d, uint64_t da, uint64_t db, int sd) {
  asm volatile("{\n.reg .pred p;\nsetp.ne.b32 p, %130, 0;\n"
    "wgmma.mma_async.sync.aligned.m64n256k16.f32.bf16.bf16 {%0,%1,%2,%3,%4,%5,%6,%7,%8,%9,%10,%11,%12,%13,%14,%15,%16,%17,%18,%19,%20,%21,%22,%23,%24,%25,%26,%27,%28,%29,%30,%31,%32,%33,%34,%35,%36,%37,%38,%39,%40,%41,%42,%43,%44,%45,%46,%47,%48,%49,%50,%51,%52,%53,%54,%55,%56,%57,%58,%59,%60,%61,%62,%63,%64,%65,%66,%67,%68,%69,%70,%71,%72,%73,%74,%75,%76,%77,%78,%79,%80,%81,%82,%83,%84,%85,%86,%87,%88,%89,%90,%91,%92,%93,%94,%95,%96,%97,%98,%99,%100,%101,%102,%103,%104,%105,%106,%107,%108,%109,%110,%111,%112,%113,%114,%115,%116,%117,%118,%119,%120,%121,%122,%123,%124,%125,%126,%127}, %128, %129, p, 1, 1, 0, %131;\n}\n"
    : "+f"(d[0]),"+f"(d[1]),"+f"(d[2]),"+f"(d[3]),"+f"(d[4]),"+f"(d[5]),"+f"(d[6]),"+f"(d[7]),"+f"(d[8]),"+f"(d[9]),"+f"(d[10]),"+f"(d[11]),"+f"(d[12]),"+f"(d[13]),"+f"(d[14]),"+f"(d[15]),"+f"(d[16]),"+f"(d[17]),"+f"(d[18]),"+f"(d[19]),"+f"(d[20]),"+f"(d[21]),"+f"(d[22]),"+f"(d[23]),"+f"(d[24]),"+f"(d[25]),"+f"(d[26]),"+f"(d[27]),"+f"(d[28]),"+f"(d[29]),"+f"(d[30]),"+f"(d[31]),"+f"(d[32]),"+f"(d[33]),"+f"(d[34]),"+f"(d[35]),"+f"(d[36]),"+f"(d[37]),"+f"(d[38]),"+f"(d[39]),"+f"(d[40]),"+f"(d[41]),"+f"(d[42]),"+f"(d[43]),"+f"(d[44]),"+f"(d[45]),"+f"(d[46]),"+f"(d[47]),"+f"(d[48]),"+f"(d[49]),"+f"(d[50]),"+f"(d[51]),"+f"(d[52]),"+f"(d[53]),"+f"(d[54]),"+f"(d[55]),"+f"(d[56]),"+f"(d[57]),"+f"(d[58]),"+f"(d[59]),"+f"(d[60]),"+f"(d[61]),"+f"(d[62]),"+f"(d[63]),"+f"(d[64]),"+f"(d[65]),"+f"(d[66]),"+f"(d[67]),"+f"(d[68]),"+f"(d[69]),"+f"(d[70]),"+f"(d[71]),"+f"(d[72]),"+f"(d[73]),"+f"(d[74]),"+f"(d[75]),"+f"(d[76]),"+f"(d[77]),"+f"(d[78]),"+f"(d[79]),"+f"(d[80]),"+f"(d[81]),"+f"(d[82]),"+f"(d[83]),"+f"(d[84]),"+f"(d[85]),"+f"(d[86]),"+f"(d[87]),"+f"(d[88]),"+f"(d[89]),"+f"(d[90]),"+f"(d[91]),"+f"(d[92]),"+f"(d[93]),"+f"(d[94]),"+f"(d[95]),"+f"(d[96]),"+f"(d[97]),"+f"(d[98]),"+f"(d[99]),"+f"(d[100]),"+f"(d[101]),"+f"(d[102]),"+f"(d[103]),"+f"(d[104]),"+f"(d[105]),"+f"(d[106]),"+f"(d[107]),"+f"(d[108]),"+f"(d[109]),"+f"(d[110]),"+f"(d[111]),"+f"(d[112]),"+f"(d[113]),"+f"(d[114]),"+f"(d[115]),"+f"(d[116]),"+f"(d[117]),"+f"(d[118]),"+f"(d[119]),"+f"(d[120]),"+f"(d[121]),"+f"(d[122]),"+f"(d[123]),"+f"(d[124]),"+f"(d[125]),"+f"(d[126]),"+f"(d[127])
    : "l"(da), "l"(db), "r"(sd), "n"(TB));
}
template<int TB> __device__ __forceinline__ void wgmma_ss_192(float* d, uint64_t da, uint64_t db, int sd) {
  asm volatile("{\n.reg .pred p;\nsetp.ne.b32 p, %98, 0;\n"
    "wgmma.mma_async.sync.aligned.m64n192k16.f32.bf16.bf16 {%0,%1,%2,%3,%4,%5,%6,%7,%8,%9,%10,%11,%12,%13,%14,%15,%16,%17,%18,%19,%20,%21,%22,%23,%24,%25,%26,%27,%28,%29,%30,%31,%32,%33,%34,%35,%36,%37,%38,%39,%40,%41,%42,%43,%44,%45,%46,%47,%48,%49,%50,%51,%52,%53,%54,%55,%56,%57,%58,%59,%60,%61,%62,%63,%64,%65,%66,%67,%68,%69,%70,%71,%72,%73,%74,%75,%76,%77,%78,%79,%80,%81,%82,%83,%84,%85,%86,%87,%88,%89,%90,%91,%92,%93,%94,%95}, %96, %97, p, 1, 1, 0, %99;\n}\n"
    : "+f"(d[0]),"+f"(d[1]),"+f"(d[2]),"+f"(d[3]),"+f"(d[4]),"+f"(d[5]),"+f"(d[6]),"+f"(d[7]),"+f"(d[8]),"+f"(d[9]),"+f"(d[10]),"+f"(d[11]),"+f"(d[12]),"+f"(d[13]),"+f"(d[14]),"+f"(d[15]),"+f"(d[16]),"+f"(d[17]),"+f"(d[18]),"+f"(d[19]),"+f"(d[20]),"+f"(d[21]),"+f"(d[22]),"+f"(d[23]),"+f"(d[24]),"+f"(d[25]),"+f"(d[26]),"+f"(d[27]),"+f"(d[28]),"+f"(d[29]),"+f"(d[30]),"+f"(d[31]),"+f"(d[32]),"+f"(d[33]),"+f"(d[34]),"+f"(d[35]),"+f"(d[36]),"+f"(d[37]),"+f"(d[38]),"+f"(d[39]),"+f"(d[40]),"+f"(d[41]),"+f"(d[42]),"+f"(d[43]),"+f"(d[44]),"+f"(d[45]),"+f"(d[46]),"+f"(d[47]),"+f"(d[48]),"+f"(d[49]),"+f"(d[50]),"+f"(d[51]),"+f"(d[52]),"+f"(d[53]),"+f"(d[54]),"+f"(d[55]),"+f"(d[56]),"+f"(d[57]),"+f"(d[58]),"+f"(d[59]),"+f"(d[60]),"+f"(d[61]),"+f"(d[62]),"+f"(d[63]),"+f"(d[64]),"+f"(d[65]),"+f"(d[66]),"+f"(d[67]),"+f"(d[68]),"+f"(d[69]),"+f"(d[70]),"+f"(d[71]),"+f"(d[72]),"+f"(d[73]),"+f"(d[74]),"+f"(d[75]),"+f"(d[76]),"+f"(d[77]),"+f"(d[78]),"+f"(d[79]),"+f"(d[80]),"+f"(d[81]),"+f"(d[82]),"+f"(d[83]),"+f"(d[84]),"+f"(d[85]),"+f"(d[86]),"+f"(d[87]),"+f"(d[88]),"+f"(d[89]),"+f"(d[90]),"+f"(d[91]),"+f"(d[92]),"+f"(d[93]),"+f"(d[94]),"+f"(d[95])
    : "l"(da), "l"(db), "r"(sd), "n"(TB));
}
template<int TB> __device__ __forceinline__ void wgmma_ss_112(float* d, uint64_t da, uint64_t db, int sd) {
  asm volatile("{\n.reg .pred p;\nsetp.ne.b32 p, %58, 0;\n"
    "wgmma.mma_async.sync.aligned.m64n112k16.f32.bf16.bf16 {%0,%1,%2,%3,%4,%5,%6,%7,%8,%9,%10,%11,%12,%13,%14,%15,%16,%17,%18,%19,%20,%21,%22,%23,%24,%25,%26,%27,%28,%29,%30,%31,%32,%33,%34,%35,%36,%37,%38,%39,%40,%41,%42,%43,%44,%45,%46,%47,%48,%49,%50,%51,%52,%53,%54,%55}, %56, %57, p, 1, 1, 0, %59;\n}\n"
    : "+f"(d[0]),"+f"(d[1]),"+f"(d[2]),"+f"(d[3]),"+f"(d[4]),"+f"(d[5]),"+f"(d[6]),"+f"(d[7]),"+f"(d[8]),"+f"(d[9]),"+f"(d[10]),"+f"(d[11]),"+f"(d[12]),"+f"(d[13]),"+f"(d[14]),"+f"(d[15]),"+f"(d[16]),"+f"(d[17]),"+f"(d[18]),"+f"(d[19]),"+f"(d[20]),"+f"(d[21]),"+f"(d[22]),"+f"(d[23]),"+f"(d[24]),"+f"(d[25]),"+f"(d[26]),"+f"(d[27]),"+f"(d[28]),"+f"(d[29]),"+f"(d[30]),"+f"(d[31]),"+f"(d[32]),"+f"(d[33]),"+f"(d[34]),"+f"(d[35]),"+f"(d[36]),"+f"(d[37]),"+f"(d[38]),"+f"(d[39]),"+f"(d[40]),"+f"(d[41]),"+f"(d[42]),"+f"(d[43]),"+f"(d[44]),"+f"(d[45]),"+f"(d[46]),"+f"(d[47]),"+f"(d[48]),"+f"(d[49]),"+f"(d[50]),"+f"(d[51]),"+f"(d[52]),"+f"(d[53]),"+f"(d[54]),"+f"(d[55])
    : "l"(da), "l"(db), "r"(sd), "n"(TB));
}
template<int TB> __device__ __forceinline__ void wgmma_rs_112(float* d, uint32_t a0, uint32_t a1, uint32_t a2, uint32_t a3, uint64_t db, int sd) {
  asm volatile("{\n.reg .pred p;\nsetp.ne.b32 p, %61, 0;\n"
    "wgmma.mma_async.sync.aligned.m64n112k16.f32.bf16.bf16 {%0,%1,%2,%3,%4,%5,%6,%7,%8,%9,%10,%11,%12,%13,%14,%15,%16,%17,%18,%19,%20,%21,%22,%23,%24,%25,%26,%27,%28,%29,%30,%31,%32,%33,%34,%35,%36,%37,%38,%39,%40,%41,%42,%43,%44,%45,%46,%47,%48,%49,%50,%51,%52,%53,%54,%55}, {%56,%57,%58,%59}, %60, p, 1, 1, %62;\n}\n"
    : "+f"(d[0]),"+f"(d[1]),"+f"(d[2]),"+f"(d[3]),"+f"(d[4]),"+f"(d[5]),"+f"(d[6]),"+f"(d[7]),"+f"(d[8]),"+f"(d[9]),"+f"(d[10]),"+f"(d[11]),"+f"(d[12]),"+f"(d[13]),"+f"(d[14]),"+f"(d[15]),"+f"(d[16]),"+f"(d[17]),"+f"(d[18]),"+f"(d[19]),"+f"(d[20]),"+f"(d[21]),"+f"(d[22]),"+f"(d[23]),"+f"(d[24]),"+f"(d[25]),"+f"(d[26]),"+f"(d[27]),"+f"(d[28]),"+f"(d[29]),"+f"(d[30]),"+f"(d[31]),"+f"(d[32]),"+f"(d[33]),"+f"(d[34]),"+f"(d[35]),"+f"(d[36]),"+f"(d[37]),"+f"(d[38]),"+f"(d[39]),"+f"(d[40]),"+f"(d[41]),"+f"(d[42]),"+f"(d[43]),"+f"(d[44]),"+f"(d[45]),"+f"(d[46]),"+f"(d[47]),"+f"(d[48]),"+f"(d[49]),"+f"(d[50]),"+f"(d[51]),"+f"(d[52]),"+f"(d[53]),"+f"(d[54]),"+f"(d[55])
    : "r"(a0), "r"(a1), "r"(a2), "r"(a3), "l"(db), "r"(sd), "n"(TB));
}

constexpr int DM = 448;
constexpr int NCTA = 128;
#define MAPPING 1
#define GRID 132
#define PINGPONG 0
#define MAP_S 4
constexpr int SPIN_LIMIT = 1 << 22;

constexpr uint32_t OFF_X = 0, OFF_Y = 114688, OFF_MISC = 229376, SMEM_BYTES = 232448;
constexpr uint32_t Y_VR = 0, Y_K = 28672, Y_KOWN = 57344, Y_VOWN = 71680, Y_Q = 86016;
constexpr uint32_t HALF = 57344;
constexpr uint32_t M_BAR = OFF_MISC;
constexpr uint32_t M_ST = OFF_MISC + 512;
constexpr uint32_t M_G = OFF_MISC + 2304;
constexpr uint32_t M_EPOCH = OFF_MISC + 3040;
enum { B_XFULL = 0, B_FULLK = 7, B_FULLV = 8, B_FULLQ, B_KRFULL, B_VRFULL, B_WOFULL, B_XCH, B_FULL = 16,
       B_EMPTY = 32, B_XFREE = B_EMPTY + 12, B_GEMV, B_PUBK, B_PUBV, B_PUBA, B_PUBB, B_PEER, B_DONE,
       B_MOD1 = 56, B_MOD2, B_WMFREE, B_WMFULL, B_HRDY };

__device__ uint32_t g_ticket;
__device__ __align__(128) uint32_t g_mod[8 * 6 * DM];
__device__ uint32_t g_flagK[16 * 8 * 8], g_flagV[16 * 8 * 8], g_flagH[16 * 8 * 2 * 8];
__device__ __align__(128) uint32_t g_kv[17 * 8 * 2 * 3584];
constexpr int XB = 34 * 32 * 128;
__device__ __align__(128) uint4 g_o[2 * XB];
__device__ __align__(128) uint4 g_x1[2 * XB];
__device__ __align__(128) uint32_t g_h2[17 * 224 * 512];
#define PROF(role, id)
#define PROFC(id)
#define PROFG(id)

struct alignas(64) Params {
    CUtensorMap wm, xm, qkv, wo, ga, ua, gb, ub, dn;
    const bf16 *x, *c, *wqkv, *wmod, *wg, *wu, *wd, *wop;
    bf16* out;
    uint32_t zero;
};

__device__ __forceinline__ void mbar_init(uint32_t bar, int cnt) { asm volatile("mbarrier.init.shared::cta.b64 [%0], %1;" ::"r"(bar), "r"(cnt) : "memory"); }
__device__ __forceinline__ void mbar_expect_tx(uint32_t bar, uint32_t bytes) { asm volatile("mbarrier.arrive.expect_tx.shared::cta.b64 _, [%0], %1;" ::"r"(bar), "r"(bytes) : "memory"); }
__device__ __forceinline__ void mbar_arrive(uint32_t bar) { asm volatile("mbarrier.arrive.shared::cta.b64 _, [%0];" ::"r"(bar) : "memory"); }
__device__ __forceinline__ void mbar_wait(uint32_t bar, uint32_t parity) {
    uint32_t ok; int n = 0;
    do {
        asm volatile("{\n.reg .pred p;\nmbarrier.try_wait.parity.shared::cta.b64 p, [%1], %2;\nselp.u32 %0, 1, 0, p;\n}" : "=r"(ok) : "r"(bar), "r"(parity) : "memory");
        if (++n > SPIN_LIMIT) __trap();
    } while (!ok);
}
__device__ __forceinline__ void mbar_wait_cluster(uint32_t bar, uint32_t parity) {
    uint32_t ok; int n = 0;
    do {
        asm volatile("{\n.reg .pred p;\nmbarrier.try_wait.parity.acquire.cluster.shared::cta.b64 p, [%1], %2;\nselp.u32 %0, 1, 0, p;\n}" : "=r"(ok) : "r"(bar), "r"(parity) : "memory");
        if (++n > SPIN_LIMIT) __trap();
    } while (!ok);
}
__device__ __forceinline__ void warp_arrive(uint32_t bar) {
    __syncwarp();
    asm volatile("{\n.reg .pred p;\nelect.sync _|p, 0xffffffff;\n@p mbarrier.arrive.shared::cta.b64 _, [%0];\n}" ::"r"(bar) : "memory");
}
__device__ __forceinline__ int opaque(int v) { return __shfl_sync(~0u, v, 0); }
__device__ __forceinline__ int fresh_tid() { int v; asm volatile("mov.u32 %0, %%tid.x;" : "=r"(v)); return v; }
__device__ __forceinline__ void bar_sync(int id, int n) { asm volatile("bar.sync %0, %1;" ::"r"(id), "r"(n) : "memory"); }
__device__ __forceinline__ void bar_arrive(int id, int n) { asm volatile("bar.arrive %0, %1;" ::"r"(id), "r"(n) : "memory"); }
__device__ __forceinline__ void fence_async_smem() { asm volatile("fence.proxy.async.shared::cta;" ::: "memory"); }
__device__ __forceinline__ void fence_async_global() { asm volatile("fence.proxy.async.global;" ::: "memory"); }
__device__ __forceinline__ void fence_gpu() { asm volatile("fence.acq_rel.gpu;" ::: "memory"); }
__device__ __forceinline__ void tma3(uint32_t dst, const CUtensorMap* m, int c0, int c1, int c2, uint32_t bar) {
    asm volatile("cp.async.bulk.tensor.3d.shared::cluster.global.mbarrier::complete_tx::bytes [%0], [%1, {%3, %4, %5}], [%2];"
                 ::"r"(dst), "l"(m), "r"(bar), "r"(c0), "r"(c1), "r"(c2) : "memory");
}
__device__ __forceinline__ void bulk_load(uint32_t dst, const void* src, uint32_t bytes, uint32_t bar) {
    asm volatile("cp.async.bulk.shared::cluster.global.mbarrier::complete_tx::bytes [%0], [%1], %2, [%3];" ::"r"(dst), "l"(src), "r"(bytes), "r"(bar) : "memory");
}
__device__ __forceinline__ void expect_e(uint32_t bar, uint32_t bytes) {
    asm volatile("{\n.reg .pred p;\nelect.sync _|p, 0xffffffff;\n@p mbarrier.arrive.expect_tx.shared::cta.b64 _, [%0], %1;\n}" ::"r"(bar), "r"(bytes) : "memory");
}
__device__ __forceinline__ void tma3_e(uint32_t dst, const CUtensorMap* m, int c0, int c1, int c2, uint32_t bar) {
    asm volatile("{\n.reg .pred p;\nelect.sync _|p, 0xffffffff;\n@p cp.async.bulk.tensor.3d.shared::cluster.global.mbarrier::complete_tx::bytes [%0], [%1, {%3, %4, %5}], [%2];\n}"
                 ::"r"(dst), "l"(m), "r"(bar), "r"(c0), "r"(c1), "r"(c2) : "memory");
}
__device__ __forceinline__ void bulk_e(uint32_t dst, const void* src, uint32_t bytes, uint32_t bar) {
    asm volatile("{\n.reg .pred p;\nelect.sync _|p, 0xffffffff;\n@p cp.async.bulk.shared::cluster.global.mbarrier::complete_tx::bytes [%0], [%1], %2, [%3];\n}"
                 ::"r"(dst), "l"(src), "r"(bytes), "r"(bar) : "memory");
}
__device__ __forceinline__ void init_e(uint32_t bar, int cnt) {
    asm volatile("{\n.reg .pred p;\nelect.sync _|p, 0xffffffff;\n@p mbarrier.init.shared::cta.b64 [%0], %1;\n}" ::"r"(bar), "r"(cnt) : "memory");
}
__device__ __forceinline__ void l2_prefetch(const void* src, uint32_t bytes) { asm volatile("cp.async.bulk.prefetch.L2.global [%0], %1;" ::"l"(src), "r"(bytes) : "memory"); }
__device__ __forceinline__ uint32_t ld_relaxed(const uint32_t* p) { uint32_t v; asm volatile("ld.relaxed.gpu.global.u32 %0, [%1];" : "=r"(v) : "l"(p) : "memory"); return v; }
__device__ __forceinline__ void st_relaxed(uint32_t* p, uint32_t v) { asm volatile("st.relaxed.gpu.global.u32 [%0], %1;" ::"l"(p), "r"(v) : "memory"); }
__device__ __forceinline__ uint4 ld_relaxed4(const uint4* p) { uint4 v; asm volatile("ld.relaxed.gpu.global.v4.u32 {%0,%1,%2,%3}, [%4];" : "=r"(v.x), "=r"(v.y), "=r"(v.z), "=r"(v.w) : "l"(p) : "memory"); return v; }
__device__ __forceinline__ void st_relaxed4(uint4* p, uint4 v) { asm volatile("st.relaxed.gpu.global.v4.u32 [%0], {%1,%2,%3,%4};" ::"l"(p), "r"(v.x), "r"(v.y), "r"(v.z), "r"(v.w) : "memory"); }
__device__ __forceinline__ uint4 ldg_nc4(const void* p) { uint4 v; asm volatile("ld.global.nc.L1::no_allocate.v4.u32 {%0,%1,%2,%3}, [%4];" : "=r"(v.x), "=r"(v.y), "=r"(v.z), "=r"(v.w) : "l"(p)); return v; }
__device__ __forceinline__ uint32_t ldg_nc(const void* p) { uint32_t v; asm volatile("ld.global.nc.u32 %0, [%1];" : "=r"(v) : "l"(p)); return v; }
__device__ __forceinline__ uint32_t ld_acquire(const uint32_t* p) { uint32_t v; asm volatile("ld.acquire.gpu.global.u32 %0, [%1];" : "=r"(v) : "l"(p) : "memory"); return v; }
__device__ __forceinline__ uint4 lds4(uint32_t a) { uint4 v; asm volatile("ld.shared.v4.u32 {%0,%1,%2,%3}, [%4];" : "=r"(v.x), "=r"(v.y), "=r"(v.z), "=r"(v.w) : "r"(a) : "memory"); return v; }
__device__ __forceinline__ float2 lds2f(uint32_t a) { float2 v; asm volatile("ld.shared.v2.f32 {%0,%1}, [%2];" : "=f"(v.x), "=f"(v.y) : "r"(a) : "memory"); return v; }
__device__ __forceinline__ uint32_t lds1(uint32_t a) { uint32_t v; asm volatile("ld.shared.u32 %0, [%1];" : "=r"(v) : "r"(a) : "memory"); return v; }
__device__ __forceinline__ void sts4(uint32_t a, uint4 v) { asm volatile("st.shared.v4.u32 [%0], {%1,%2,%3,%4};" ::"r"(a), "r"(v.x), "r"(v.y), "r"(v.z), "r"(v.w) : "memory"); }
__device__ __forceinline__ void sts2(uint32_t a, uint32_t x, uint32_t y) { asm volatile("st.shared.v2.u32 [%0], {%1,%2};" ::"r"(a), "r"(x), "r"(y) : "memory"); }
__device__ __forceinline__ void sts1(uint32_t a, uint32_t v) { asm volatile("st.shared.u32 [%0], %1;" ::"r"(a), "r"(v) : "memory"); }
__device__ __forceinline__ void stsm4(uint32_t a, uint32_t r0, uint32_t r1, uint32_t r2, uint32_t r3) {
    asm volatile("stmatrix.sync.aligned.m8n8.x4.shared.b16 [%0], {%1,%2,%3,%4};" ::"r"(a), "r"(r0), "r"(r1), "r"(r2), "r"(r3));
}
__device__ __forceinline__ uint32_t pack2(float lo, float hi) { uint32_t r; asm("cvt.rn.bf16x2.f32 %0, %1, %2;" : "=r"(r) : "f"(hi), "f"(lo)); return r; }
__device__ __forceinline__ uint32_t pack2_relu(float lo, float hi) { uint32_t r; asm("cvt.rn.relu.bf16x2.f32 %0, %1, %2;" : "=r"(r) : "f"(hi), "f"(lo)); return r; }
__device__ __forceinline__ uint32_t hfma2(uint32_t a, uint32_t b, uint32_t c) { uint32_t r; asm("fma.rn.bf16x2 %0, %1, %2, %3;" : "=r"(r) : "r"(a), "r"(b), "r"(c)); return r; }
__device__ __forceinline__ uint32_t hmul2(uint32_t a, uint32_t b) { uint32_t r; asm("mul.rn.bf16x2 %0, %1, %2;" : "=r"(r) : "r"(a), "r"(b)); return r; }
__device__ __forceinline__ float bf_lo(uint32_t v) { return __uint_as_float(v << 16); }
__device__ __forceinline__ float bf_hi(uint32_t v) { return __uint_as_float(v & 0xFFFF0000u); }
__device__ __forceinline__ float bf_round(float v) { return bf_lo(pack2(v, 0.f)); }
__device__ __forceinline__ float ex2(float x) { float r; asm("ex2.approx.ftz.f32 %0, %1;" : "=f"(r) : "f"(x)); return r; }
__device__ __forceinline__ void mma16816(float* d, uint32_t a0, uint32_t a1, uint32_t a2, uint32_t a3, uint32_t b0, uint32_t b1) {
    asm("mma.sync.aligned.m16n8k16.row.col.f32.bf16.bf16.f32 {%0,%1,%2,%3}, {%4,%5,%6,%7}, {%8,%9}, {%0,%1,%2,%3};"
        : "+f"(d[0]), "+f"(d[1]), "+f"(d[2]), "+f"(d[3]) : "r"(a0), "r"(a1), "r"(a2), "r"(a3), "r"(b0), "r"(b1));
}
__device__ __forceinline__ void mma16816_first(float* d, uint32_t a0, uint32_t a1, uint32_t a2, uint32_t a3, uint32_t b0, uint32_t b1) {
    asm volatile("mma.sync.aligned.m16n8k16.row.col.f32.bf16.bf16.f32 {%0,%1,%2,%3}, {%4,%5,%6,%7}, {%8,%9}, {%10,%10,%10,%10};"
        : "=f"(d[0]), "=f"(d[1]), "=f"(d[2]), "=f"(d[3]) : "r"(a0), "r"(a1), "r"(a2), "r"(a3), "r"(b0), "r"(b1), "f"(0.f));
}
__device__ __forceinline__ void mma16816_v(float* d, uint32_t a0, uint32_t a1, uint32_t a2, uint32_t a3, uint32_t b0, uint32_t b1) {
    asm volatile("mma.sync.aligned.m16n8k16.row.col.f32.bf16.bf16.f32 {%0,%1,%2,%3}, {%4,%5,%6,%7}, {%8,%9}, {%0,%1,%2,%3};"
        : "+f"(d[0]), "+f"(d[1]), "+f"(d[2]), "+f"(d[3]) : "r"(a0), "r"(a1), "r"(a2), "r"(a3), "r"(b0), "r"(b1));
}
__device__ __forceinline__ void mma1688(float* d, uint32_t a0, uint32_t a1, uint32_t b0) {
    asm("mma.sync.aligned.m16n8k8.row.col.f32.bf16.bf16.f32 {%0,%1,%2,%3}, {%4,%5}, {%6}, {%0,%1,%2,%3};"
        : "+f"(d[0]), "+f"(d[1]), "+f"(d[2]), "+f"(d[3]) : "r"(a0), "r"(a1), "r"(b0));
}
__device__ __forceinline__ void ldsm4(uint32_t a, uint32_t* r) {
    asm volatile("ldmatrix.sync.aligned.m8n8.x4.shared.b16 {%0,%1,%2,%3}, [%4];" : "=r"(r[0]), "=r"(r[1]), "=r"(r[2]), "=r"(r[3]) : "r"(a));
}
__device__ __forceinline__ void ldsm4t(uint32_t a, uint32_t* r) {
    asm volatile("ldmatrix.sync.aligned.m8n8.x4.trans.shared.b16 {%0,%1,%2,%3}, [%4];" : "=r"(r[0]), "=r"(r[1]), "=r"(r[2]), "=r"(r[3]) : "r"(a));
}
__device__ __forceinline__ float rcp(float x) { float r; asm("rcp.approx.ftz.f32 %0, %1;" : "=f"(r) : "f"(x)); return r; }
__device__ __forceinline__ uint2 ld_relaxed2(const void* p) { uint2 v; asm volatile("ld.relaxed.gpu.global.v2.u32 {%0,%1}, [%2];" : "=r"(v.x), "=r"(v.y) : "l"(p) : "memory"); return v; }
__device__ __forceinline__ void st_relaxed2(void* p, uint32_t x, uint32_t y) { asm volatile("st.relaxed.gpu.global.v2.u32 [%0], {%1,%2};" ::"l"(p), "r"(max(x, 1u)), "r"(max(y, 1u)) : "memory"); }
__device__ __forceinline__ constexpr uint64_t dconst(uint32_t lbo, uint32_t sbo, uint32_t swz) {
    return ((uint64_t)(lbo >> 4) << 16) | ((uint64_t)(sbo >> 4) << 32) | ((uint64_t)swz << 62);
}
__device__ __forceinline__ uint64_t mkdesc(uint32_t addr, uint64_t c) { return c | (uint64_t)((addr & 0x3FFFF) >> 4); }
#define WG_FENCE() asm volatile("wgmma.fence.sync.aligned;" ::: "memory")
#define WG_COMMIT() asm volatile("wgmma.commit_group.sync.aligned;" ::: "memory")
#define WG_WAIT(n) asm volatile("wgmma.wait_group.sync.aligned %0;" ::"n"(n) : "memory")
template <int N> __device__ __forceinline__ void reg_fence(float* d) {
#pragma unroll
    for (int i = 0; i < N; i++) asm volatile("" : "+f"(d[i])::"memory");
}
template <int N> __device__ __forceinline__ void reg_def(float* d) {
#pragma unroll
    for (int i = 0; i < N; i++) asm volatile("" : "=f"(d[i]));
}
template <int N> __device__ __forceinline__ void reg_def(uint32_t* d) {
#pragma unroll
    for (int i = 0; i < N; i++) asm volatile("" : "=r"(d[i]));
}
__device__ __forceinline__ bool is_unset(uint4 v) { return min(min(v.x, v.y), min(v.z, v.w)) == 0u; }
__device__ __forceinline__ uint4 nz4(uint32_t a, uint32_t b, uint32_t c, uint32_t d) { return make_uint4(max(a, 1u), max(b, 1u), max(c, 1u), max(d, 1u)); }
__device__ __forceinline__ void wait_flag(const uint32_t* p, uint32_t target) {
    int n = 0;
    while ((int)(ld_acquire(p) - target) < 0) { if (++n > SPIN_LIMIT) __trap(); }
}
__device__ __forceinline__ float silu_bf(uint32_t cbits) {
    const float c = __uint_as_float(cbits << 16);
    return bf_round(__fdividef(c, 1.f + fminf(ex2(-1.4426950408889634f * c), 1e30f)));
}
__device__ __forceinline__ void gemv_part(uint32_t wmbuf, int npanel, int wp, int lane) {
    const uint32_t wa = wmbuf + wp * 512 + (8 * (lane >> 4) + (lane & 7)) * 32 + ((lane >> 3) & 1) * 16;
    uint2 B[4];
#pragma unroll
    for (int i = 0; i < 4; i++) { const float2 v = lds2f(wmbuf + 28672 + (wp + 8 * i) * 32 + (lane & 3) * 8); B[i] = make_uint2(__float_as_uint(v.x), __float_as_uint(v.y)); }
#pragma unroll 1
    for (int pn = 0; pn < npanel; pn++) {
        float d[4] = {};
        uint32_t A[16];
#pragma unroll
        for (int i = 0; i < 4; i++) ldsm4t(wa + pn * 14336 + (i < 3 || wp < 4 ? i : 0) * 4096, A + 4 * i);
#pragma unroll
        for (int i = 0; i < 4; i++) mma16816(d, A[4 * i], A[4 * i + 1], A[4 * i + 2], A[4 * i + 3], B[i].x, B[i].y);
        if ((lane & 3) == 0) {
            sts1(wmbuf + 29696 + (wp * 32 + pn * 16 + (lane >> 2)) * 4, __float_as_uint(d[0]));
            sts1(wmbuf + 29696 + (wp * 32 + pn * 16 + 8 + (lane >> 2)) * 4, __float_as_uint(d[2]));
        }
    }
}
__device__ __forceinline__ void ln_coeffs(float mean, float msq, uint32_t& r2, uint32_t& n2) {
    const float rs = bf_round(rsqrtf(fmaxf(msq - mean * mean, 0.f) + 1e-5f));
    r2 = pack2(rs, rs);
    n2 = pack2(-mean * rs, -mean * rs);
}

__global__ void __cluster_dims__(2, 1, 1) __launch_bounds__(384, 1) fused_block_kernel(const __grid_constant__ Params p) {
    extern __shared__ __align__(1024) unsigned char smem[];
    const uint32_t sb = (uint32_t)__cvta_generic_to_shared(smem);
    const int tid = threadIdx.x, lane = tid & 31, warp = __shfl_sync(~0u, tid >> 5, 0);
    const int m = blockIdx.x >> 1;
#define kh (j & 1)
    int r, nq;
    {
        int g, i;
        if (m < MAP_S) { g = m < 4 ? 15 : 16; i = m & 3; }
        else if (m < MAP_S + 32) { g = (m - MAP_S) & 7; i = (m - MAP_S) >> 3; }
        else if (m < MAP_S + 60) { i = (m - MAP_S - 32) / 7; g = 8 + (m - MAP_S - 32) - 7 * i; }
        else { g = 16; i = m & 3; }
        r = g; nq = i;
    }
    const int j = opaque(2 * nq + (blockIdx.x & 1)), b = 8 * r + j, fs = 4 * kh + nq;
    const uint32_t sc = r == 16;
#define BAR(i) (sb + M_BAR + 8 * (i))
    if (lane == 0 && warp < 9 && warp != 6 && warp != 7) {
        const int i0 = warp == 8 ? 0 : 8 + 8 * warp, cnt = warp == 0 || warp == 8 ? 1 : warp < 3 ? 2 : 8;
#pragma unroll
        for (int k = 0; k < 8; k++) mbar_init(BAR(i0 + k), cnt);
        asm volatile("fence.mbarrier_init.release.cluster;" ::: "memory");
        fence_async_smem();
    }

    if (warp < 8) {
        const int w = warp >> 2, wi = warp & 3;
#define COORDS const int t = fresh_tid() & 127, lane = t & 31, q = lane & 3, lr = lane >> 2, ra = 64 * w + 16 * wi + lr; \
        const uint32_t lx = (lane >> 4) ^ (lane & 7), mrow = (64 * w + 16 * wi + ((lane >> 3) & 1) * 8 + (lane & 7)) * 128; \
        (void)q; (void)lr; (void)ra; (void)lx; (void)mrow;
#define XOFF ((lds1(sb + M_EPOCH) & 1) * XB + t)
        const int sid = 2 * (j & 3) + w;
#define RUN(k) (!sc || sid == (k))
#define WAIT(i, par) mbar_wait(BAR(i), (par) | sc)
        constexpr uint64_t DA128 = dconst(16, 1024, 1), DB128 = dconst(4096, 1024, 1);
        bar_arrive(9, 384);
        bar_sync(0, 384);
        asm volatile("barrier.cluster.arrive.relaxed.aligned;" ::: "memory");
        asm volatile("setmaxnreg.inc.sync.aligned.u32 224;");
        PROFC(0); PROFG(30);
        uint32_t xr[16];
        {
            COORDS
            uint32_t h[112];
            if (RUN(0)) {
                float ds[4] = {}, da[2][4] = {}, db[2][4] = {};
                const uint32_t ONE2 = 0x3F803F80u;
                if (kh == 0) { WAIT(B_WMFULL, 0); gemv_part(sb + OFF_Y + HALF, 1, warp, lane); warp_arrive(BAR(B_GEMV)); }
#pragma unroll
                for (int kb = 0; kb < 7; kb++) {
                    WAIT(B_XFULL + kb, 0);
#pragma unroll
                    for (int k4 = 0; k4 < 4; k4++) ldsm4(sb + OFF_X + mrow + kb * 16384 + (((2 * k4) ^ lx) << 4), h + 16 * kb + 4 * k4);
#pragma unroll
                    for (int k4 = 0; k4 < 4; k4++) {
                        const uint32_t* f = h + 16 * kb + 4 * k4;
                        mma16816(ds, f[0], f[1], f[2], f[3], ONE2, ONE2);
                        mma1688(da[0], f[0], f[1], f[0]); mma1688(db[0], f[0], f[1], f[1]);
                        mma1688(da[1], f[2], f[3], f[2]); mma1688(db[1], f[2], f[3], f[3]);
                    }
                }
#pragma unroll
                for (int i = 0; i < 4; i++) {
                    const int ch = 7 * j + 2 * i + (lane >> 4);
                    ldsm4(sb + OFF_X + mrow + (ch >> 3) * 16384 + (((ch ^ lane) & 7) << 4), xr + 4 * i);
                }
                warp_arrive(BAR(B_XFREE));
                PROFC(27);
                float qa = (lr & 1) ? da[0][1] + da[1][1] : da[0][0] + da[1][0];
                float qb = (lr & 1) ? db[0][3] + db[1][3] : db[0][2] + db[1][2];
                const int src = (lane & ~3) | (lr >> 1);
                qa = __shfl_sync(~0u, qa, src);
                qb = __shfl_sync(~0u, qb, src);
                uint32_t ra2, na2, rb2, nb2;
                ln_coeffs(ds[0] * (1.f / DM), qa * (1.f / DM), ra2, na2);
                ln_coeffs(ds[2] * (1.f / DM), qb * (1.f / DM), rb2, nb2);
#pragma unroll
                for (int i = 0; i < 112; i += 2) { h[i] = hfma2(h[i], ra2, na2); h[i + 1] = hfma2(h[i + 1], rb2, nb2); }
                if (kh == 1) { WAIT(B_WMFULL, 0); gemv_part(sb + OFF_Y + HALF, 2, warp, lane); warp_arrive(BAR(B_GEMV)); }
            } else { reg_def<112>(h); reg_def<16>(xr); }
            PROFC(1);
            if (RUN(1)) {
                float ak[28], av[28], aq[28];
                uint32_t kp[14], vp[14];
                const uint64_t bk0 = mkdesc(sb + OFF_Y, DB128) + kh, bv0 = mkdesc(sb + OFF_Y + HALF, DB128) + kh, bq0 = mkdesc(sb + OFF_X, DB128) + kh;
                uint32_t* kvg = g_kv + (size_t)(b * 2) * 3584 + (8 * w + 2 * wi) * 224 + lane;
                WAIT(B_FULLK, 0);
                WAIT(B_MOD1, 0);
                PROFC(2);
                reg_def<28>(ak);
#pragma unroll
                for (int g4 = 0; g4 < 4; g4++) {
#pragma unroll
                    for (int ks = 7 * g4; ks < 7 * g4 + 7; ks++) {
                        const uint4 st = *(const uint4*)(smem + M_ST + ks * 64 + q * 16);
                        h[4 * ks] = hfma2(h[4 * ks], st.x, st.y); h[4 * ks + 1] = hfma2(h[4 * ks + 1], st.x, st.y);
                        h[4 * ks + 2] = hfma2(h[4 * ks + 2], st.z, st.w); h[4 * ks + 3] = hfma2(h[4 * ks + 3], st.z, st.w);
                    }
                    WG_FENCE();
#pragma unroll
                    for (int ks = 7 * g4; ks < 7 * g4 + 7; ks++) wgmma_rs_56<1>(ak, h[4 * ks], h[4 * ks + 1], h[4 * ks + 2], h[4 * ks + 3], bk0 + ks * 128, ks != 0);
                }
                WG_COMMIT();
                PROFC(3);
                WAIT(B_FULLV, 0);
                reg_def<28>(av);
                WG_FENCE();
#pragma unroll
                for (int ks = 0; ks < 8; ks++) wgmma_rs_56<1>(av, h[4 * ks], h[4 * ks + 1], h[4 * ks + 2], h[4 * ks + 3], bv0 + ks * 128, ks != 0);
                WG_COMMIT();
                WG_WAIT(1);
                reg_fence<28>(ak);
#pragma unroll
                for (int g = 0; g < 7; g++) {
                    kp[2 * g] = pack2(ak[4 * g], ak[4 * g + 1]); kp[2 * g + 1] = pack2(ak[4 * g + 2], ak[4 * g + 3]);
                    kvg[g * 32] = kp[2 * g]; kvg[224 + g * 32] = kp[2 * g + 1];
                }
                warp_arrive(BAR(B_PUBK));
                PROFC(4);
                WG_FENCE();
#pragma unroll
                for (int ks = 8; ks < 28; ks++) wgmma_rs_56<1>(av, h[4 * ks], h[4 * ks + 1], h[4 * ks + 2], h[4 * ks + 3], bv0 + ks * 128, 1);
                WG_COMMIT();
                WAIT(B_FULLQ, 0);
                reg_def<28>(aq);
                WG_FENCE();
#pragma unroll
                for (int ks = 0; ks < 8; ks++) wgmma_rs_56<1>(aq, h[4 * ks], h[4 * ks + 1], h[4 * ks + 2], h[4 * ks + 3], bq0 + ks * 128, ks != 0);
                WG_COMMIT();
                WG_WAIT(1);
                reg_fence<28>(av);
#pragma unroll
                for (int g = 0; g < 7; g++) {
                    vp[2 * g] = pack2(av[4 * g], av[4 * g + 1]); vp[2 * g + 1] = pack2(av[4 * g + 2], av[4 * g + 3]);
                    kvg[3584 + g * 32] = vp[2 * g]; kvg[3584 + 224 + g * 32] = vp[2 * g + 1];
                }
                warp_arrive(BAR(B_PUBV));
                PROFC(5);
                WG_FENCE();
#pragma unroll
                for (int ks = 8; ks < 28; ks++) wgmma_rs_56<1>(aq, h[4 * ks], h[4 * ks + 1], h[4 * ks + 2], h[4 * ks + 3], bq0 + ks * 128, 1);
                WG_COMMIT();
                WAIT(B_PUBV, 0);
                const uint32_t ko = sb + OFF_Y + Y_KOWN + (8 * w + 2 * wi) * 896 + lane * 4;
                const uint32_t qo = sb + OFF_Y + Y_Q + (8 * w + 2 * wi) * 1024 + lane * 4;
#pragma unroll
                for (int g = 0; g < 7; g++) {
                    sts1(ko + g * 128, kp[2 * g]); sts1(ko + 896 + g * 128, kp[2 * g + 1]);
                    sts1(ko + (Y_VOWN - Y_KOWN) + g * 128, vp[2 * g]); sts1(ko + (Y_VOWN - Y_KOWN) + 896 + g * 128, vp[2 * g + 1]);
                }
                WG_WAIT(0);
                reg_fence<28>(aq);
                __syncwarp();
                if (lane < 3) mbar_arrive(BAR(B_EMPTY + lane));
#pragma unroll
                for (int g = 0; g < 7; g++) {
                    const uint32_t q0 = pack2(aq[4 * g], aq[4 * g + 1]), q1 = pack2(aq[4 * g + 2], aq[4 * g + 3]);
                    if (g == 3) {
                        sts1(qo + 3 * 128, q < 2 ? q0 : 0u); sts1(qo + 1024 + 3 * 128, q < 2 ? q1 : 0u);
                        sts1(qo + 4 * 128, q < 2 ? 0u : q0); sts1(qo + 1024 + 4 * 128, q < 2 ? 0u : q1);
                    } else {
                        const int ch = g < 3 ? g : g + 1;
                        sts1(qo + ch * 128, q0); sts1(qo + 1024 + ch * 128, q1);
                    }
                }
                if (!sc) bar_sync(3, 256);
            }
        }
        PROFC(6);
        WAIT(B_KRFULL, 0);
        PROFC(7);
        if (RUN(2)) {
#pragma unroll 1
            for (int hf = sc; hf < 2; hf++) {
                COORDS
                float s[136];
                float na = 0.f, nb = 0.f;
                const float CS = 0.18898223650461361f * 1.4426950408889634f;
                const int kg0 = 8 * hf + 2 * wi;
                const int pmin = 16 - 8 * r - 4 * hf - wi;
                const float NEG = __int_as_float(0xFF800000);
                {
                    uint32_t F[8];
                    const uint32_t qa = sb + OFF_Y + Y_Q + (kg0 + ((lane >> 3) & 1)) * 1024 + (4 * w + (lane >> 4)) * 128 + (lane & 7) * 16;
                    ldsm4(qa, F); ldsm4(qa + 256, F + 4);
                    uint32_t ka = sb + OFF_Y + Y_K + kg0 * 896 + (3 * w + (lane >> 3)) * 128 + (lane & 7) * 16;
#pragma unroll
                    for (int g = 0; g < 34; g++) {
                        uint32_t B[4];
                        if (g >= 12 && g % 4 == 0) ka += __float_as_uint(s[4 * (g - 12)]) & p.zero;
                        ldsm4(ka + g * 896, B);
                        mma16816_first(s + 4 * g, F[0], F[1], F[2], F[3], B[0], B[1]);
                        mma16816_v(s + 4 * g, F[4], F[5], F[6], F[7], B[2], B[3]);
                    }
                    const bool c0 = 2 * q > lr, c1 = 2 * q + 1 > lr;
                    if (!c0) { s[0] = NEG; s[6] = NEG; }
                    if (!c1) { s[1] = NEG; s[7] = NEG; }
                    s[2] = NEG; s[3] = NEG;
                    if (c0) { s[128] = NEG; s[134] = NEG; }
                    if (c1) { s[129] = NEG; s[135] = NEG; }
                    s[132] = NEG; s[133] = NEG;
                    float ma = NEG, mb = NEG;
#pragma unroll
                    for (int pp = 0; pp < 17; pp++) {
                        const float* e = s + 8 * pp;
                        const float bias = pp < pmin ? NEG : 0.f;
                        ma = fmaxf(ma, fmaxf(fmaxf(e[0], e[1]), fmaxf(e[4], e[5])) + bias);
                        mb = fmaxf(mb, fmaxf(fmaxf(e[2], e[3]), fmaxf(e[6], e[7])) + bias);
                    }
                    ma = fmaxf(ma, __shfl_xor_sync(~0u, ma, 1)); mb = fmaxf(mb, __shfl_xor_sync(~0u, mb, 1));
                    ma = fmaxf(ma, __shfl_xor_sync(~0u, ma, 2)); mb = fmaxf(mb, __shfl_xor_sync(~0u, mb, 2));
                    na = -ma * CS; nb = -mb * CS;
                }
                PROFC(8 + 3 * hf);
                {
                    if (hf == 0) mbar_wait(BAR(B_VRFULL), 0);
                    float o[16] = {}, rs[4] = {};
                    const uint32_t va = sb + OFF_Y + Y_VR + (kg0 + ((lane >> 3) & 1)) * 896 + (3 * w + (lane >> 4)) * 128 + (lane & 7) * 16;
#pragma unroll
                    for (int pp = 0; pp < 17; pp++) {
                        uint32_t B[8];
                        const uint32_t v = va + pp * 1792 + (pp == 16 || (pp >= 9 && kg0 + 2 * pp >= 32) ? Y_VOWN - 32 * 896 : 0);
                        ldsm4t(v, B); ldsm4t(v + 256, B + 4);
                        float e[8];
#pragma unroll
                        for (int i = 0; i < 8; i++) e[i] = ex2(fmaf(s[8 * pp + i], CS, ((i & 2) ? nb : na) + (pp < pmin ? NEG : 0.f)));
                        const uint32_t p0 = pack2(e[0], e[1]), p1 = pack2(e[2], e[3]), p2 = pack2(e[4], e[5]), p3 = pack2(e[6], e[7]);
                        mma16816(rs, p0, p1, p2, p3, 0x3F803F80u, 0x3F803F80u);
#pragma unroll
                        for (int g = 0; g < 4; g++) mma16816(o + 4 * g, p0, p1, p2, p3, B[2 * g], B[2 * g + 1]);
                    }
                    PROFC(9 + 3 * hf);
                    const float ia = rcp(rs[0]), ib = rcp(rs[2]);
                    char* og = (char*)(g_o + (size_t)(2 * r + hf) * 32 * 128 + XOFF);
#pragma unroll
                    for (int g = 0; g < 4; g++) {
                        const int G = 7 * j + 3 * w + g;
                        const bool on = (g == 3 - 3 * w) ? ((q >> 1) == w) : true;
                        if (on) st_relaxed2(og + (G >> 1) * 2048 + (G & 1) * 8, pack2(o[4 * g] * ia, o[4 * g + 1] * ia), pack2(o[4 * g + 2] * ib, o[4 * g + 3] * ib));
                    }
                    PROFC(10 + 3 * hf);
                }
            }
        }
        if (!sc) bar_arrive(6 + w, 256);
        uint32_t x1p[14];
        COORDS
        const int xoff = XOFF;
        if (RUN(4)) {
            uint4 af[28];
            reg_def<112>((uint32_t*)af);
            const uint4* og = g_o + (size_t)(2 * r + w) * 32 * 128 + xoff;
            {
                const int G = 7 * ((lane & 15) >> 1) + 2 + 4 * (lane & 1);
                const char* pp = (const char*)og + (G >> 1) * 2048 + (G & 1) * 8;
                uint32_t done = 0;
#pragma unroll 1
                for (int n = 0; done != 0x1111u; n++) {
                    const uint2 v = ld_relaxed2(pp);
                    uint32_t ok = __ballot_sync(~0u, min(v.x, v.y) != 0u || sc);
                    ok &= ok >> 16; ok &= ok >> 2; ok &= ok >> 1; ok &= 0x1111u & ~done;
#pragma unroll
                    for (int u = 0; u < 4; u++)
                        if ((ok >> (4 * u)) & 1) {
#pragma unroll
                            for (int i = 7 * u; i < 7 * u + 7; i++) af[i] = ld_relaxed4(og + i * 128);
                        }
                    done |= ok;
                    if (n > SPIN_LIMIT) __trap();
                }
            }
            PROFC(28);
            WAIT(B_WOFULL, 0);
            float ac[28];
            const uint64_t bd = mkdesc(sb + OFF_X + HALF, DB128) + kh;
            reg_def<28>(ac);
#pragma unroll
            for (int u = 0; u < 4; u++) {
#pragma unroll 1
                for (int n = 0;; n++) {
                    uint32_t mn = ~0u;
#pragma unroll
                    for (int i = 7 * u; i < 7 * u + 7; i++) mn = min(mn, min(min(af[i].x, af[i].y), min(af[i].z, af[i].w)));
                    if (!__any_sync(~0u, mn == 0u) || sc) break;
#pragma unroll
                    for (int i = 7 * u; i < 7 * u + 7; i++) af[i] = ld_relaxed4(og + i * 128);
                    if (n > SPIN_LIMIT) __trap();
                }
                WG_FENCE();
#pragma unroll
                for (int i = 7 * u; i < 7 * u + 7; i++) wgmma_rs_56<1>(ac, af[i].x, af[i].y, af[i].z, af[i].w, bd + i * 128, i != 0);
                WG_COMMIT();
            }
            PROFC(14);
            WAIT(B_MOD2, 0);
            WG_WAIT(0);
            reg_fence<28>(ac);
            float s1a = 0.f, s2a = 0.f, s1b = 0.f, s2b = 0.f;
#pragma unroll
            for (int g = 0; g < 7; g++) {
                const float2 ga = *(const float2*)(smem + M_G + (8 * g + 2 * q) * 4);
                x1p[2 * g] = pack2(fmaf(ga.x, ac[4 * g], bf_lo(xr[2 * g])), fmaf(ga.y, ac[4 * g + 1], bf_hi(xr[2 * g])));
                x1p[2 * g + 1] = pack2(fmaf(ga.x, ac[4 * g + 2], bf_lo(xr[2 * g + 1])), fmaf(ga.y, ac[4 * g + 3], bf_hi(xr[2 * g + 1])));
                const float u0 = bf_lo(x1p[2 * g]), u1 = bf_hi(x1p[2 * g]), u2 = bf_lo(x1p[2 * g + 1]), u3 = bf_hi(x1p[2 * g + 1]);
                s1a += u0 + u1; s2a += u0 * u0 + u1 * u1; s1b += u2 + u3; s2b += u2 * u2 + u3 * u3;
            }
            uint4* xo = g_x1 + (size_t)(((2 * r + w) * 8 + j) * 4) * 128 + xoff;
            st_relaxed4(xo, nz4(x1p[0], x1p[1], x1p[2], x1p[3]));
            st_relaxed4(xo + 128, nz4(x1p[4], x1p[5], x1p[6], x1p[7]));
            st_relaxed4(xo + 256, nz4(x1p[8], x1p[9], x1p[10], x1p[11]));
            float ka = (q & 1) ? s2a : s1a, kb2 = (q & 1) ? s2b : s1b;
            ka += __shfl_xor_sync(~0u, (q & 1) ? s1a : s2a, 1); kb2 += __shfl_xor_sync(~0u, (q & 1) ? s1b : s2b, 1);
            ka += __shfl_xor_sync(~0u, ka, 2); kb2 += __shfl_xor_sync(~0u, kb2, 2);
            st_relaxed4(xo + 384, nz4(x1p[12], x1p[13], __float_as_uint(ka), __float_as_uint(kb2)));
        } else reg_def<14>(x1p);
        PROFC(15);
        if (RUN(5)) {
            uint4 xf[32];
            reg_def<128>((uint32_t*)xf);
            const uint4* xg = g_x1 + (size_t)((2 * r + w) * 32) * 128 + xoff;
            const uint4* pp = xg + (4 * (lane & 7) + 3) * 128;
            uint32_t done = 0;
#pragma unroll 1
            for (int n = 0;; n++) {
                uint32_t ok = __ballot_sync(~0u, !is_unset(ld_relaxed4(pp)) || sc);
                ok &= ok >> 16; ok &= ok >> 8; ok &= 0xFFu & ~done;
#pragma unroll
                for (int u = 0; u < 8; u++)
                    if ((ok >> u) & 1) {
#pragma unroll
                        for (int i = 4 * u; i < 4 * u + 4; i++) xf[i] = ld_relaxed4(xg + i * 128);
                    }
                done |= ok;
                if (done == 0xFFu) {
                    PROFC(16);
                    uint32_t mn = ~0u;
#pragma unroll
                    for (int i = 0; i < 32; i++) mn = min(mn, min(min(xf[i].x, xf[i].y), min(xf[i].z, xf[i].w)));
                    if (!__any_sync(~0u, mn == 0u) || sc) break;
                    done = 0;
                }
                if (n > SPIN_LIMIT) __trap();
            }
            PROFC(29);
            if (lane < 4) mbar_arrive(BAR(B_EMPTY + 3 + lane));
            float ka = 0.f, kb2 = 0.f;
#pragma unroll
            for (int jj = 0; jj < 8; jj++) { ka += __uint_as_float(xf[4 * jj + 3].z); kb2 += __uint_as_float(xf[4 * jj + 3].w); }
            const float oa = __shfl_xor_sync(~0u, ka, 1), ob = __shfl_xor_sync(~0u, kb2, 1);
            uint32_t ra2, na2, rb2, nb2;
            ln_coeffs(((q & 1) ? oa : ka) * (1.f / DM), ((q & 1) ? ka : oa) * (1.f / DM), ra2, na2);
            ln_coeffs(((q & 1) ? ob : kb2) * (1.f / DM), ((q & 1) ? kb2 : ob) * (1.f / DM), rb2, nb2);
            uint32_t* xw = (uint32_t*)xf;
            if (!sc) bar_sync(7 - w, 256);
#pragma unroll
            for (int G8 = 0; G8 < 56; G8 += 8) {
#pragma unroll
                for (int G = G8; G < G8 + 8; G += 2) {
                    const uint4 st = *(const uint4*)(smem + M_ST + (G >> 1) * 64 + q * 16);
                    const int i0 = (G / 7) * 16 + (G % 7) * 2, i1 = ((G + 1) / 7) * 16 + ((G + 1) % 7) * 2;
                    xw[i0] = hfma2(hfma2(xw[i0], ra2, na2), st.x, st.y); xw[i0 + 1] = hfma2(hfma2(xw[i0 + 1], rb2, nb2), st.x, st.y);
                    xw[i1] = hfma2(hfma2(xw[i1], ra2, na2), st.z, st.w); xw[i1 + 1] = hfma2(hfma2(xw[i1 + 1], rb2, nb2), st.z, st.w);
                }
#pragma unroll
                for (int G = G8; G < G8 + 8; G += 2) {
                    const int i0 = (G / 7) * 16 + (G % 7) * 2, i1 = ((G + 1) / 7) * 16 + ((G + 1) % 7) * 2;
                    stsm4(sb + OFF_Y + mrow + (G >> 3) * 16384 + (((G & 7) ^ lx) << 4), xw[i0], xw[i0 + 1], xw[i1], xw[i1 + 1]);
                }
            }
            fence_async_smem();
            bar_sync(1 + w, 128);
        }
        PROFC(17);
        uint32_t h2a[32], h2b[24];
        if (RUN(6)) {
            const int fa = 224 * fs + ((fs & 1) ? 96 : 0), fb = 224 * fs + ((fs & 1) ? 0 : 128);
            uint32_t* h2g = g_h2 + (size_t)r * (224 * 512) + (8 * w + 2 * wi) * 32 + lane;
            const uint64_t a0 = mkdesc(sb + OFF_Y + w * 8192, DA128);
            const int s0 = sc ? 12 : 0;
            {
                float ac[128];
                reg_def<128>(ac);
                int sl = 0, prev = 0;
#pragma unroll 1
                for (int s = s0; s < 14; s++) {
                    WAIT(B_FULL + sl, s >= 7);
                    const uint64_t ad = a0 + (s >> 1) * 1024 + (s & 1) * 4, bd = mkdesc(sb + OFF_X + sl * 16384, DB128);
                    WG_FENCE();
                    wgmma_ss_256<1>(ac, ad, bd, s != 0);
                    wgmma_ss_256<1>(ac, ad + 2, bd + 128, 1);
                    WG_COMMIT();
                    if (s > 0) { WG_WAIT(1); warp_arrive(BAR(B_EMPTY + prev)); }
                    prev = sl; sl = sl == 6 ? 0 : sl + 1;
                }
                WG_WAIT(0);
                reg_fence<128>(ac);
                warp_arrive(BAR(B_EMPTY + 6));
                PROFC(18);
#pragma unroll
                for (int g = 0; g < 16; g++) {
                    h2a[2 * g] = hmul2(pack2_relu(ac[4 * g], ac[4 * g + 1]), pack2(ac[64 + 4 * g], ac[64 + 4 * g + 1]));
                    h2a[2 * g + 1] = hmul2(pack2_relu(ac[4 * g + 2], ac[4 * g + 3]), pack2(ac[64 + 4 * g + 2], ac[64 + 4 * g + 3]));
                    h2g[(fa / 8 + g) * 512] = h2a[2 * g]; h2g[(fa / 8 + g) * 512 + 32] = h2a[2 * g + 1];
                }
                warp_arrive(BAR(B_PUBA));
            }
            PROFC(19);
            {
                float ac[96];
                reg_def<96>(ac);
                int sl = 0, prev = 0;
#pragma unroll 1
                for (int s = s0; s < 14; s++) {
                    WAIT(B_FULL + sl, s >= 7);
                    const uint64_t ad = a0 + (s >> 1) * 1024 + (s & 1) * 4, bd = mkdesc(sb + OFF_X + sl * 16384, dconst(2048, 512, 2));
                    WG_FENCE();
                    wgmma_ss_192<1>(ac, ad, bd, s != 0);
                    wgmma_ss_192<1>(ac, ad + 2, bd + 64, 1);
                    WG_COMMIT();
                    if (s > 0) { WG_WAIT(1); warp_arrive(BAR(B_EMPTY + prev)); }
                    prev = sl; sl = sl == 6 ? 0 : sl + 1;
                }
                WG_WAIT(0);
                reg_fence<96>(ac);
                __syncwarp();
                if (lane < 6) mbar_arrive(BAR(B_EMPTY + 6 + lane));
                asm volatile("barrier.cluster.wait.aligned;" ::: "memory");
                if (lane == 0 && !sc) {
                    uint32_t rb;
                    asm volatile("mapa.shared::cluster.u32 %0, %1, %2;" : "=r"(rb) : "r"(BAR(B_PEER)), "r"(kh ^ 1));
                    asm volatile("mbarrier.arrive.relaxed.cluster.shared::cluster.b64 _, [%0];" ::"r"(rb) : "memory");
                }
                PROFC(20);
#pragma unroll
                for (int g = 0; g < 12; g++) {
                    h2b[2 * g] = hmul2(pack2_relu(ac[4 * g], ac[4 * g + 1]), pack2(ac[48 + 4 * g], ac[48 + 4 * g + 1]));
                    h2b[2 * g + 1] = hmul2(pack2_relu(ac[4 * g + 2], ac[4 * g + 3]), pack2(ac[48 + 4 * g + 2], ac[48 + 4 * g + 3]));
                    h2g[(fb / 8 + g) * 512] = h2b[2 * g]; h2g[(fb / 8 + g) * 512 + 32] = h2b[2 * g + 1];
                }
                warp_arrive(BAR(B_PUBB));
            }
        } else { reg_def<32>(h2a); reg_def<24>(h2b); }
        PROFC(21);
        if (RUN(7)) {
            float ac[56];
            reg_def<56>(ac);
            constexpr uint64_t DAN = dconst(2048, 128, 0);
#pragma unroll 1
            for (int u = 0; u < 12; u++) {
                WAIT(B_FULL + u, 0);
                const uint32_t sl = sb + u * 16384;
                const uint64_t ad = mkdesc(sl + 8192 + w * 1024, DAN), bd = mkdesc(sl, DB128);
                WG_FENCE();
                wgmma_ss_112<1>(ac, ad, bd, u != 0);
                wgmma_ss_112<1>(ac, ad + 256, bd + 128, 1);
                WG_COMMIT();
                if (u > 0) { WG_WAIT(1); warp_arrive(BAR(B_EMPTY + u - 1)); }
            }
            PROFC(22);
#pragma unroll
            for (int u = 0; u < 7; u++) {
                WAIT(B_FULL + u, 1);
                const uint64_t bd = mkdesc(sb + u * 16384, DB128);
                const uint32_t* hh = u < 4 ? h2a + 8 * u : h2b + 8 * (u - 4);
                WG_FENCE();
                wgmma_rs_112<1>(ac, hh[0], hh[1], hh[2], hh[3], bd, 1);
                wgmma_rs_112<1>(ac, hh[4], hh[5], hh[6], hh[7], bd + 128, 1);
                WG_COMMIT();
                if (u > 0 && u < 5) { WG_WAIT(1); warp_arrive(BAR(B_EMPTY + u - 1)); }
                if (u == 0) { WG_WAIT(1); warp_arrive(BAR(B_EMPTY + 11)); }
            }
            PROFC(23);
#pragma unroll 1
            for (int u = 7; u < 16; u++) {
                const int sli = u < 12 ? u : u - 12;
                WAIT(B_FULL + sli, u < 12);
                const uint32_t sl = sb + sli * 16384;
                const uint64_t ad = mkdesc(sl + 8192 + w * 1024, DAN), bd = mkdesc(sl, DB128);
                WG_FENCE();
                wgmma_ss_112<1>(ac, ad, bd, 1);
                wgmma_ss_112<1>(ac, ad + 256, bd + 128, 1);
                WG_COMMIT();
            }
            mbar_wait_cluster(BAR(B_PEER), sc);
            WG_WAIT(0);
            reg_fence<56>(ac);
            PROFC(24);
            uint32_t rdst, rbar;
            asm volatile("mapa.shared::cluster.u32 %0, %1, %2;" : "=r"(rdst) : "r"(sb + OFF_Y + (5 + w) * 16384 + t * 16), "r"(kh ^ 1 ^ sc));
            asm volatile("mapa.shared::cluster.u32 %0, %1, %2;" : "=r"(rbar) : "r"(BAR(B_XCH + w)), "r"(kh ^ 1 ^ sc));
#pragma unroll
            for (int g = 0; g < 7; g++) {
                const float v0 = kh ? ac[4 * g] : ac[28 + 4 * g], v1 = kh ? ac[4 * g + 1] : ac[28 + 4 * g + 1];
                const float v2 = kh ? ac[4 * g + 2] : ac[28 + 4 * g + 2], v3 = kh ? ac[4 * g + 3] : ac[28 + 4 * g + 3];
                if (!sc) asm volatile("st.async.shared::cluster.mbarrier::complete_tx::bytes.v4.f32 [%0], {%1,%2,%3,%4}, [%5];"
                             ::"r"(rdst + g * 2048), "f"(v0), "f"(v1), "f"(v2), "f"(v3), "r"(rbar) : "memory");
            }
            mbar_wait_cluster(BAR(B_XCH + w), sc);
            PROFC(25);
            bf16* og = (sc ? (bf16*)(g_h2 + 16 * 224 * 512) : p.out + (size_t)128 * r * DM) + (size_t)ra * DM + 56 * j + 2 * q;
#pragma unroll
            for (int g = 0; g < 7; g++) {
                const uint4 rv = *(const uint4*)(smem + OFF_Y + (5 + w) * 16384 + t * 16 + g * 2048);
                const float2 gb = *(const float2*)(smem + M_G + 224 + (8 * g + 2 * q) * 4);
                const float v0 = (kh ? ac[28 + 4 * g] : ac[4 * g]) + __uint_as_float(rv.x), v1 = (kh ? ac[28 + 4 * g + 1] : ac[4 * g + 1]) + __uint_as_float(rv.y);
                const float v2 = (kh ? ac[28 + 4 * g + 2] : ac[4 * g + 2]) + __uint_as_float(rv.z), v3 = (kh ? ac[28 + 4 * g + 3] : ac[4 * g + 3]) + __uint_as_float(rv.w);
                *(uint32_t*)(og + 8 * g) = pack2(fmaf(gb.x, v0, bf_lo(x1p[2 * g])), fmaf(gb.y, v1, bf_hi(x1p[2 * g])));
                *(uint32_t*)(og + 8 * DM + 8 * g) = pack2(fmaf(gb.x, v2, bf_lo(x1p[2 * g + 1])), fmaf(gb.y, v3, bf_hi(x1p[2 * g + 1])));
            }
        }
        PROFC(26); PROFG(31);
        warp_arrive(BAR(B_DONE));
    } else {
        const int lane = fresh_tid() & 31;
        const bool early = kh == 0, gemv = r < 14;
        const int mcol = early ? 16 * (4 * r + nq) : 2 * DM + 32 * (4 * r + nq);
        const uint32_t wmbuf = sb + OFF_Y + HALF;
        const int fa = 224 * fs + ((fs & 1) ? 96 : 0), fb = 224 * fs + ((fs & 1) ? 0 : 128);
        asm volatile("setmaxnreg.dec.sync.aligned.u32 56;");
        if (warp == 9) {
            init_e(BAR(B_MOD1), 2); init_e(BAR(B_MOD2), 2); init_e(BAR(B_HRDY), 1); init_e(BAR(B_HRDY + 1), 1); init_e(BAR(B_WMFREE), 1);
        }
        if (warp == 8) { init_e(BAR(B_WMFULL), 2); fence_async_smem(); }
        bar_arrive(0, 384);
        asm volatile("barrier.cluster.arrive.relaxed.aligned;" ::: "memory");
        uint32_t target = 0;
        if (warp == 8) {
            PROF(2, 0);
            if (!sc) {
                expect_e(BAR(B_WMFULL), gemv ? 28672 >> early : 0);
                if (early && gemv) { tma3_e(wmbuf, &p.wm, mcol, 0, 0, BAR(B_WMFULL)); tma3_e(wmbuf + 7168, &p.wm, mcol, 224, 0, BAR(B_WMFULL)); }
#pragma unroll 1
                for (int kb = 0; kb < 7; kb++) {
                    expect_e(BAR(B_XFULL + kb), 16384);
                    tma3_e(sb + OFF_X + kb * 16384, &p.xm, 64 * kb, 128 * r, 0, BAR(B_XFULL + kb));
                }
            }
            PROF(2, 1);
#pragma unroll 1
            for (int mt = 0; mt < 4; mt++) {
                if (mt == 1) {
                    if (!early && gemv) {
#pragma unroll 1
                        for (int k = 0; k < 4; k++) tma3_e(wmbuf + k * 7168, &p.wm, mcol + (k >> 1) * 16, (k & 1) * 224, 0, BAR(B_WMFULL));
                    }
                    bar_sync(9, 384);
                    if (sc) return;
                    mbar_wait(BAR(B_MOD1), 0);
                    mbar_wait(BAR(B_WMFREE), 0);
                }
                if (mt == 2) mbar_wait(BAR(B_XFREE), 0);
                if (mt == 3) mbar_wait(BAR(B_VRFULL), 0);
                const uint32_t bar = BAR(mt == 3 ? B_WOFULL : B_FULLK + mt), dst = sb + (mt < 2 ? OFF_Y : OFF_X) + (mt & 1) * HALF;
                const int c0 = (mt < 2 ? DM + DM * mt : 0) + 56 * j - 8 * kh;
                if (!sc) {
                    expect_e(bar, HALF);
                    tma3_e(dst, mt == 3 ? &p.wo : &p.qkv, c0, 0, 0, bar);
                    tma3_e(dst + HALF / 2, mt == 3 ? &p.wo : &p.qkv, c0, 224, 0, bar);
                }
                PROF(2, 5 + mt);
            }
            expect_e(BAR(B_XCH), 14336);
            expect_e(BAR(B_XCH + 1), 14336);
        } else {
            if (warp == 10 && lane == 0 && !sc) {
                const uint32_t ticket = atomicAdd(&g_ticket, 1u);
                l2_prefetch((const char*)p.wqkv + (size_t)b * 9408, 9408);
                sts1(sb + M_EPOCH, ticket / NCTA);
            }
            if (warp == 11) {
#pragma unroll
                for (int i = 0; i < 8; i++) {
                    const int wd = lane + 32 * i;
                    const uint32_t cb = i < 7 ? __ldg((const uint32_t*)p.c + wd) : 0u;
                    sts1(wmbuf + 28672 + (wd >> 3) * 32 + (wd & 3) * 8 + (wd & 4), pack2(silu_bf(cb & 0xFFFFu), silu_bf(cb >> 16)));
                }
            }
            bar_sync(9, 384);
            if (sc) return;
            target = lds1(sb + M_EPOCH) + 1;
            const uint32_t tag = target & 0xFFFFu;
            if (warp == 11) {
                warp_arrive(BAR(B_WMFULL));
                mbar_wait(BAR(B_GEMV), 0);
                PROF(3, 9);
                float sum = 0.f;
#pragma unroll
                for (int i = 0; i < 8; i++) sum += *(const float*)(smem + OFF_Y + HALF + 29696 + (i * 32 + (early ? lane & 15 : lane)) * 4);
                const uint32_t word = (pack2(sum, 0.f) << 16) | tag;
                if (gemv) {
                    uint32_t* mg = g_mod + mcol + (early ? (lane & 15) + (lane >> 4) * 4 * 6 * DM : lane);
#pragma unroll
                    for (int i = 0; i < 8; i++) if (i < 4 || !early) st_relaxed(mg + i * 6 * DM, word);
                }
                warp_arrive(BAR(B_WMFREE));
                PROF(3, 0);
            }
            const uint4* modp = (const uint4*)g_mod + (r & 7) * (6 * DM / 4);
            const bool p2 = warp == 11;
            mbar_wait(BAR(p2 ? B_PUBK : B_XFULL + 4), 0);
#pragma unroll 1
            for (int it = p2 ? 0 : warp - 9; it < (p2 ? 2 : warp - 8); it++) {
                const int i0 = lane + 32 * it, imax = p2 ? 251 : 223;
                uint4 v[4];
#pragma unroll 1
                for (int n = 0;; n++) {
                    uint32_t bad = 0;
#pragma unroll
                    for (int k = 0; k < 4; k++) {
                        const int i = min(i0 + 64 * k, imax);
                        v[k] = ld_relaxed4(modp + (i < 224 ? (p2 ? 336 : 0) + i : (i < 238 ? 14 * j + i : 14 * j + i + 322)));
                        bad |= (v[k].x ^ tag) | (v[k].y ^ tag) | (v[k].z ^ tag) | (v[k].w ^ tag);
                    }
                    if (!(bad & 0xFFFFu)) break;
                    if (n > SPIN_LIMIT) __trap();
                }
#pragma unroll
                for (int k = 0; k < 4; k++) {
                    const int i = min(i0 + 64 * k, imax);
                    if (i < 224) {
                        const int isc = i >= 112, c4 = i - 112 * isc;
                        const float one = isc ? 1.f : 0.f;
                        const uint32_t a = sb + M_ST + (c4 >> 2) * 64 + (c4 & 1) * 32 + (c4 & 2) * 4 + (isc ? 0 : 4);
                        sts1(a, pack2(bf_hi(v[k].x) + one, bf_hi(v[k].y) + one));
                        sts1(a + 16, pack2(bf_hi(v[k].z) + one, bf_hi(v[k].w) + one));
                    } else {
                        sts4(sb + M_G + (i - 224) * 16, make_uint4(v[k].x & 0xFFFF0000u, v[k].y & 0xFFFF0000u, v[k].z & 0xFFFF0000u, v[k].w & 0xFFFF0000u));
                    }
                }
                warp_arrive(BAR(p2 ? B_MOD2 : B_MOD1));
            }
            PROF(3, p2 ? 5 : 1);
            if (warp == 9) {
#pragma unroll 1
                for (int kv = 0; kv < 2; kv++) {
                    mbar_wait(BAR(B_PUBK + kv), 0);
                    if (lane >= 1 && lane <= 2 && r >= lane) wait_flag((kv ? g_flagV : g_flagK) + (b - 8 * lane) * 8, target);
                    __syncwarp();
                    PROF(3, 8);
                    fence_async_global();
                    const uint32_t dst = sb + OFF_Y + (kv ? Y_VR : Y_K);
                    expect_e(BAR(B_KRFULL + kv), r >= 2 ? 28672 : r == 1 ? 14336 : 0);
                    if (r >= 2) bulk_e(dst, g_kv + (size_t)((b - 16) * 2 + kv) * 3584, 14336, BAR(B_KRFULL + kv));
                    if (r >= 1) bulk_e(dst + 14336, g_kv + (size_t)((b - 8) * 2 + kv) * 3584, 14336, BAR(B_KRFULL + kv));
                    PROF(3, 2 + kv);
                }
            } else if (warp == 11) {
                mbar_wait(BAR(B_VRFULL), 0);
                if (lane == 0) {
                    l2_prefetch((const char*)p.wg + (size_t)b * 12544, 12544);
                    l2_prefetch((const char*)p.wu + (size_t)b * 12544, 12544);
                    l2_prefetch((const char*)p.wd + (size_t)b * 12544, 12544);
                }
                __syncwarp();
            }
        }
        if (warp == 8 || warp == 11) {
            const int sec = warp == 11;
            int sl = 0;
#pragma unroll 1
            for (int s = 0; s < 28; s++) {
                const bool pa = s < 14;
                const uint32_t half = pa ? 8192 : 6144;
                mbar_wait(BAR(B_EMPTY + sl), (s >= 7 && s < 14) || s >= 21);
                expect_e(BAR(B_FULL + sl), half);
                tma3_e(sb + OFF_X + sl * 16384 + sec * half, &p.ga + (pa ? 0 : 2) + sec, 0, 32 * (pa ? s : s - 14), pa ? fa >> 6 : fb >> 5, BAR(B_FULL + sl));
                sl = sl == 6 ? 0 : sl + 1;
            }
            PROF(2, 3);
            sl = 0;
            int u = 0;
#pragma unroll 1
            for (int grp = 0; grp < 8; grp++) {
                const bool pa = grp < 4, own = grp == 3 || grp == 4;
                int sidx = pa ? grp : grp - 5;
                sidx = own ? nq : sidx + (sidx >= nq);
                const int ofs = 4 * kh + sidx;
                int f = 224 * ofs + ((ofs & 1) ? (pa ? 96 : 0) : (pa ? 0 : 128));
                if (sec && (grp == 0 || grp == 5)) { mbar_wait(BAR(B_HRDY + !pa), 0); fence_async_global(); }
#pragma unroll 1
                for (int k = pa ? 0 : 1; k < 4; k++, u++, f += 32) {
                    const uint32_t dst = sb + sl * 16384, bar = BAR(B_FULL + sl);
                    mbar_wait(BAR(B_EMPTY + sl), u >= 12 && u < 24);
                    if (!sec) {
                        expect_e(bar, 8192);
                        tma3_e(dst, &p.dn, 0, nq, f, bar);
                        tma3_e(dst + 4096, &p.dn, 64, nq, f, bar);
                    } else {
                        expect_e(bar, own ? 0 : 8192);
                        if (!own) bulk_e(dst + 8192, g_h2 + (size_t)r * (224 * 512) + f * 64, 8192, bar);
                    }
                    sl = sl == 11 ? 0 : sl + 1;
                }
            }
            PROF(2, 4);
            mbar_wait(BAR(B_DONE), 0);
        } else if (warp == 9) {
            mbar_wait(BAR(B_EMPTY), 1);
            const int idle = (target & 1) * XB + (2 * r * 32 + 4 * j) * 128;
#pragma unroll 4
            for (int i = lane; i < 1024; i += 32) {
                const int k = idle + (i >> 9) * 4096 + (i & 511);
                g_o[k] = make_uint4(0, 0, 0, 0);
                g_x1[k] = make_uint4(0, 0, 0, 0);
            }
#pragma unroll 1
            for (int ps = 0; ps < 2; ps++) {
                mbar_wait(BAR(B_PUBA + ps), 0);
                if (lane < 4) wait_flag(&g_flagH[((r * 8 + 4 * kh + lane) * 2 + ps) * 8], target);
                warp_arrive(BAR(B_HRDY + ps));
                PROF(3, 6 + ps);
            }
        } else {
            if (lane == 0) {
#pragma unroll 1
                for (int k = 0; k < 4; k++) {
                    mbar_wait(BAR(B_PUBK + k), 0);
                    if (k == 0) PROF(3, 10);
                    fence_gpu();
                    st_relaxed(k == 0 ? &g_flagK[b * 8] : k == 1 ? &g_flagV[b * 8] : &g_flagH[((r * 8 + fs) * 2 + k - 2) * 8], target);
                    if (k == 0) PROF(3, 11);
                }
            }
        }
    }
}

typedef CUresult (*EncodeFn)(CUtensorMap*, CUtensorMapDataType, cuuint32_t, void*, const cuuint64_t*, const cuuint64_t*, const cuuint32_t*,
                             const cuuint32_t*, CUtensorMapInterleave, CUtensorMapSwizzle, CUtensorMapL2promotion, CUtensorMapFloatOOBfill);

static void make_map(EncodeFn fn, CUtensorMap* m, const void* ptr, uint64_t d0, uint64_t d1, uint64_t d2, uint64_t s1, uint64_t s2,
                     uint32_t b0, uint32_t b1, uint32_t b2, CUtensorMapSwizzle sw) {
    cuuint64_t dims[3] = {d0, d1, d2}, strides[2] = {s1, s2};
    cuuint32_t box[3] = {b0, b1, b2}, es[3] = {1, 1, 1};
    CUresult rc = fn(m, CU_TENSOR_MAP_DATA_TYPE_BFLOAT16, 3, (void*)ptr, dims, strides, box, es, CU_TENSOR_MAP_INTERLEAVE_NONE, sw,
                     CU_TENSOR_MAP_L2_PROMOTION_L2_128B, CU_TENSOR_MAP_FLOAT_OOB_FILL_NONE);
    (void)rc;
}

extern "C" void kernel_launch(void* const* d_in, const int* in_sizes, int n_in, void* d_out, int out_size) {
    (void)in_sizes; (void)n_in; (void)out_size;
    static EncodeFn fn = nullptr;
    if (!fn) {
        cudaDriverEntryPointQueryResult st;
        cudaGetDriverEntryPoint("cuTensorMapEncodeTiled", (void**)&fn, cudaEnableDefault, &st);
        cudaFuncSetAttribute(fused_block_kernel, cudaFuncAttributeMaxDynamicSharedMemorySize, SMEM_BYTES);
    }
    Params p;
    p.x = (const bf16*)d_in[0];
    const bf16* wqkv = (const bf16*)d_in[1];
    p.wqkv = wqkv;
    p.wop = (const bf16*)d_in[2];
    p.wg = (const bf16*)d_in[4];
    p.wu = (const bf16*)d_in[5];
    p.wd = (const bf16*)d_in[6];
    p.c = (const bf16*)d_in[7];
    p.wmod = (const bf16*)d_in[8];
    p.out = (bf16*)d_out;
    p.zero = 0;
    make_map(fn, &p.wm, p.wmod, 2688, 448, 1, 5376, 5376 * 448, 16, 224, 1, CU_TENSOR_MAP_SWIZZLE_NONE);
    make_map(fn, &p.xm, p.x, 448, 2048, 1, 896, 896 * 2048, 64, 128, 1, CU_TENSOR_MAP_SWIZZLE_128B);
    make_map(fn, &p.qkv, wqkv, 1344, 448, 1, 2688, 2688 * 448, 64, 224, 1, CU_TENSOR_MAP_SWIZZLE_128B);
    make_map(fn, &p.wo, p.wop, 448, 448, 1, 896, 896 * 448, 64, 224, 1, CU_TENSOR_MAP_SWIZZLE_128B);
    make_map(fn, &p.ga, p.wg, 64, 448, 28, 3584, 128, 64, 32, 2, CU_TENSOR_MAP_SWIZZLE_128B);
    make_map(fn, &p.ua, p.wu, 64, 448, 28, 3584, 128, 64, 32, 2, CU_TENSOR_MAP_SWIZZLE_128B);
    make_map(fn, &p.gb, p.wg, 32, 448, 56, 3584, 64, 32, 32, 3, CU_TENSOR_MAP_SWIZZLE_64B);
    make_map(fn, &p.ub, p.wu, 32, 448, 56, 3584, 64, 32, 32, 3, CU_TENSOR_MAP_SWIZZLE_64B);
    make_map(fn, &p.dn, p.wd, 112, 4, 1792, 224, 896, 64, 1, 32, CU_TENSOR_MAP_SWIZZLE_128B);
    fused_block_kernel<<<GRID, 384, SMEM_BYTES>>>(p);
}
```

```cpp
#include <cuda_runtime.h>
#include <cuda_bf16.h>
#include <cuda.h>
#include <stdint.h>

typedef __nv_bfloat16 bf16;

template<int TB> __device__ __forceinline__ void wgmma_rs_56(float* d, uint32_t a0, uint32_t a1, uint32_t a2, uint32_t a3, uint64_t db, int sd) {
  asm volatile("{\n.reg .pred p;\nsetp.ne.b32 p, %33, 0;\n"
    "wgmma.mma_async.sync.aligned.m64n56k16.f32.bf16.bf16 {%0,%1,%2,%3,%4,%5,%6,%7,%8,%9,%10,%11,%12,%13,%14,%15,%16,%17,%18,%19,%20,%21,%22,%23,%24,%25,%26,%27}, {%28,%29,%30,%31}, %32, p, 1, 1, %34;\n}\n"
    : "+f"(d[0]),"+f"(d[1]),"+f"(d[2]),"+f"(d[3]),"+f"(d[4]),"+f"(d[5]),"+f"(d[6]),"+f"(d[7]),"+f"(d[8]),"+f"(d[9]),"+f"(d[10]),"+f"(d[11]),"+f"(d[12]),"+f"(d[13]),"+f"(d[14]),"+f"(d[15]),"+f"(d[16]),"+f"(d[17]),"+f"(d[18]),"+f"(d[19]),"+f"(d[20]),"+f"(d[21]),"+f"(d[22]),"+f"(d[23]),"+f"(d[24]),"+f"(d[25]),"+f"(d[26]),"+f"(d[27])
    : "r"(a0), "r"(a1), "r"(a2), "r"(a3), "l"(db), "r"(sd), "n"(TB));
}
template<int TB> __device__ __forceinline__ void wgmma_ss_56(float* d, uint64_t da, uint64_t db, int sd) {
  asm volatile("{\n.reg .pred p;\nsetp.ne.b32 p, %30, 0;\n"
    "wgmma.mma_async.sync.aligned.m64n56k16.f32.bf16.bf16 {%0,%1,%2,%3,%4,%5,%6,%7,%8,%9,%10,%11,%12,%13,%14,%15,%16,%17,%18,%19,%20,%21,%22,%23,%24,%25,%26,%27}, %28, %29, p, 1, 1, 0, %31;\n}\n"
    : "+f"(d[0]),"+f"(d[1]),"+f"(d[2]),"+f"(d[3]),"+f"(d[4]),"+f"(d[5]),"+f"(d[6]),"+f"(d[7]),"+f"(d[8]),"+f"(d[9]),"+f"(d[10]),"+f"(d[11]),"+f"(d[12]),"+f"(d[13]),"+f"(d[14]),"+f"(d[15]),"+f"(d[16]),"+f"(d[17]),"+f"(d[18]),"+f"(d[19]),"+f"(d[20]),"+f"(d[21]),"+f"(d[22]),"+f"(d[23]),"+f"(d[24]),"+f"(d[25]),"+f"(d[26]),"+f"(d[27])
    : "l"(da), "l"(db), "r"(sd), "n"(TB));
}
template<int TB> __device__ __forceinline__ void wgmma_ss_256(float* d, uint64_t da, uint64_t db, int sd) {
  asm volatile("{\n.reg .pred p;\nsetp.ne.b32 p, %130, 0;\n"
    "wgmma.mma_async.sync.aligned.m64n256k16.f32.bf16.bf16 {%0,%1,%2,%3,%4,%5,%6,%7,%8,%9,%10,%11,%12,%13,%14,%15,%16,%17,%18,%19,%20,%21,%22,%23,%24,%25,%26,%27,%28,%29,%30,%31,%32,%33,%34,%35,%36,%37,%38,%39,%40,%41,%42,%43,%44,%45,%46,%47,%48,%49,%50,%51,%52,%53,%54,%55,%56,%57,%58,%59,%60,%61,%62,%63,%64,%65,%66,%67,%68,%69,%70,%71,%72,%73,%74,%75,%76,%77,%78,%79,%80,%81,%82,%83,%84,%85,%86,%87,%88,%89,%90,%91,%92,%93,%94,%95,%96,%97,%98,%99,%100,%101,%102,%103,%104,%105,%106,%107,%108,%109,%110,%111,%112,%113,%114,%115,%116,%117,%118,%119,%120,%121,%122,%123,%124,%125,%126,%127}, %128, %129, p, 1, 1, 0, %131;\n}\n"
    : "+f"(d[0]),"+f"(d[1]),"+f"(d[2]),"+f"(d[3]),"+f"(d[4]),"+f"(d[5]),"+f"(d[6]),"+f"(d[7]),"+f"(d[8]),"+f"(d[9]),"+f"(d[10]),"+f"(d[11]),"+f"(d[12]),"+f"(d[13]),"+f"(d[14]),"+f"(d[15]),"+f"(d[16]),"+f"(d[17]),"+f"(d[18]),"+f"(d[19]),"+f"(d[20]),"+f"(d[21]),"+f"(d[22]),"+f"(d[23]),"+f"(d[24]),"+f"(d[25]),"+f"(d[26]),"+f"(d[27]),"+f"(d[28]),"+f"(d[29]),"+f"(d[30]),"+f"(d[31]),"+f"(d[32]),"+f"(d[33]),"+f"(d[34]),"+f"(d[35]),"+f"(d[36]),"+f"(d[37]),"+f"(d[38]),"+f"(d[39]),"+f"(d[40]),"+f"(d[41]),"+f"(d[42]),"+f"(d[43]),"+f"(d[44]),"+f"(d[45]),"+f"(d[46]),"+f"(d[47]),"+f"(d[48]),"+f"(d[49]),"+f"(d[50]),"+f"(d[51]),"+f"(d[52]),"+f"(d[53]),"+f"(d[54]),"+f"(d[55]),"+f"(d[56]),"+f"(d[57]),"+f"(d[58]),"+f"(d[59]),"+f"(d[60]),"+f"(d[61]),"+f"(d[62]),"+f"(d[63]),"+f"(d[64]),"+f"(d[65]),"+f"(d[66]),"+f"(d[67]),"+f"(d[68]),"+f"(d[69]),"+f"(d[70]),"+f"(d[71]),"+f"(d[72]),"+f"(d[73]),"+f"(d[74]),"+f"(d[75]),"+f"(d[76]),"+f"(d[77]),"+f"(d[78]),"+f"(d[79]),"+f"(d[80]),"+f"(d[81]),"+f"(d[82]),"+f"(d[83]),"+f"(d[84]),"+f"(d[85]),"+f"(d[86]),"+f"(d[87]),"+f"(d[88]),"+f"(d[89]),"+f"(d[90]),"+f"(d[91]),"+f"(d[92]),"+f"(d[93]),"+f"(d[94]),"+f"(d[95]),"+f"(d[96]),"+f"(d[97]),"+f"(d[98]),"+f"(d[99]),"+f"(d[100]),"+f"(d[101]),"+f"(d[102]),"+f"(d[103]),"+f"(d[104]),"+f"(d[105]),"+f"(d[106]),"+f"(d[107]),"+f"(d[108]),"+f"(d[109]),"+f"(d[110]),"+f"(d[111]),"+f"(d[112]),"+f"(d[113]),"+f"(d[114]),"+f"(d[115]),"+f"(d[116]),"+f"(d[117]),"+f"(d[118]),"+f"(d[119]),"+f"(d[120]),"+f"(d[121]),"+f"(d[122]),"+f"(d[123]),"+f"(d[124]),"+f"(d[125]),"+f"(d[126]),"+f"(d[127])
    : "l"(da), "l"(db), "r"(sd), "n"(TB));
}
template<int TB> __device__ __forceinline__ void wgmma_ss_192(float* d, uint64_t da, uint64_t db, int sd) {
  asm volatile("{\n.reg .pred p;\nsetp.ne.b32 p, %98, 0;\n"
    "wgmma.mma_async.sync.aligned.m64n192k16.f32.bf16.bf16 {%0,%1,%2,%3,%4,%5,%6,%7,%8,%9,%10,%11,%12,%13,%14,%15,%16,%17,%18,%19,%20,%21,%22,%23,%24,%25,%26,%27,%28,%29,%30,%31,%32,%33,%34,%35,%36,%37,%38,%39,%40,%41,%42,%43,%44,%45,%46,%47,%48,%49,%50,%51,%52,%53,%54,%55,%56,%57,%58,%59,%60,%61,%62,%63,%64,%65,%66,%67,%68,%69,%70,%71,%72,%73,%74,%75,%76,%77,%78,%79,%80,%81,%82,%83,%84,%85,%86,%87,%88,%89,%90,%91,%92,%93,%94,%95}, %96, %97, p, 1, 1, 0, %99;\n}\n"
    : "+f"(d[0]),"+f"(d[1]),"+f"(d[2]),"+f"(d[3]),"+f"(d[4]),"+f"(d[5]),"+f"(d[6]),"+f"(d[7]),"+f"(d[8]),"+f"(d[9]),"+f"(d[10]),"+f"(d[11]),"+f"(d[12]),"+f"(d[13]),"+f"(d[14]),"+f"(d[15]),"+f"(d[16]),"+f"(d[17]),"+f"(d[18]),"+f"(d[19]),"+f"(d[20]),"+f"(d[21]),"+f"(d[22]),"+f"(d[23]),"+f"(d[24]),"+f"(d[25]),"+f"(d[26]),"+f"(d[27]),"+f"(d[28]),"+f"(d[29]),"+f"(d[30]),"+f"(d[31]),"+f"(d[32]),"+f"(d[33]),"+f"(d[34]),"+f"(d[35]),"+f"(d[36]),"+f"(d[37]),"+f"(d[38]),"+f"(d[39]),"+f"(d[40]),"+f"(d[41]),"+f"(d[42]),"+f"(d[43]),"+f"(d[44]),"+f"(d[45]),"+f"(d[46]),"+f"(d[47]),"+f"(d[48]),"+f"(d[49]),"+f"(d[50]),"+f"(d[51]),"+f"(d[52]),"+f"(d[53]),"+f"(d[54]),"+f"(d[55]),"+f"(d[56]),"+f"(d[57]),"+f"(d[58]),"+f"(d[59]),"+f"(d[60]),"+f"(d[61]),"+f"(d[62]),"+f"(d[63]),"+f"(d[64]),"+f"(d[65]),"+f"(d[66]),"+f"(d[67]),"+f"(d[68]),"+f"(d[69]),"+f"(d[70]),"+f"(d[71]),"+f"(d[72]),"+f"(d[73]),"+f"(d[74]),"+f"(d[75]),"+f"(d[76]),"+f"(d[77]),"+f"(d[78]),"+f"(d[79]),"+f"(d[80]),"+f"(d[81]),"+f"(d[82]),"+f"(d[83]),"+f"(d[84]),"+f"(d[85]),"+f"(d[86]),"+f"(d[87]),"+f"(d[88]),"+f"(d[89]),"+f"(d[90]),"+f"(d[91]),"+f"(d[92]),"+f"(d[93]),"+f"(d[94]),"+f"(d[95])
    : "l"(da), "l"(db), "r"(sd), "n"(TB));
}
template<int TB> __device__ __forceinline__ void wgmma_ss_112(float* d, uint64_t da, uint64_t db, int sd) {
  asm volatile("{\n.reg .pred p;\nsetp.ne.b32 p, %58, 0;\n"
    "wgmma.mma_async.sync.aligned.m64n112k16.f32.bf16.bf16 {%0,%1,%2,%3,%4,%5,%6,%7,%8,%9,%10,%11,%12,%13,%14,%15,%16,%17,%18,%19,%20,%21,%22,%23,%24,%25,%26,%27,%28,%29,%30,%31,%32,%33,%34,%35,%36,%37,%38,%39,%40,%41,%42,%43,%44,%45,%46,%47,%48,%49,%50,%51,%52,%53,%54,%55}, %56, %57, p, 1, 1, 0, %59;\n}\n"
    : "+f"(d[0]),"+f"(d[1]),"+f"(d[2]),"+f"(d[3]),"+f"(d[4]),"+f"(d[5]),"+f"(d[6]),"+f"(d[7]),"+f"(d[8]),"+f"(d[9]),"+f"(d[10]),"+f"(d[11]),"+f"(d[12]),"+f"(d[13]),"+f"(d[14]),"+f"(d[15]),"+f"(d[16]),"+f"(d[17]),"+f"(d[18]),"+f"(d[19]),"+f"(d[20]),"+f"(d[21]),"+f"(d[22]),"+f"(d[23]),"+f"(d[24]),"+f"(d[25]),"+f"(d[26]),"+f"(d[27]),"+f"(d[28]),"+f"(d[29]),"+f"(d[30]),"+f"(d[31]),"+f"(d[32]),"+f"(d[33]),"+f"(d[34]),"+f"(d[35]),"+f"(d[36]),"+f"(d[37]),"+f"(d[38]),"+f"(d[39]),"+f"(d[40]),"+f"(d[41]),"+f"(d[42]),"+f"(d[43]),"+f"(d[44]),"+f"(d[45]),"+f"(d[46]),"+f"(d[47]),"+f"(d[48]),"+f"(d[49]),"+f"(d[50]),"+f"(d[51]),"+f"(d[52]),"+f"(d[53]),"+f"(d[54]),"+f"(d[55])
    : "l"(da), "l"(db), "r"(sd), "n"(TB));
}
template<int TB> __device__ __forceinline__ void wgmma_rs_112(float* d, uint32_t a0, uint32_t a1, uint32_t a2, uint32_t a3, uint64_t db, int sd) {
  asm volatile("{\n.reg .pred p;\nsetp.ne.b32 p, %61, 0;\n"
    "wgmma.mma_async.sync.aligned.m64n112k16.f32.bf16.bf16 {%0,%1,%2,%3,%4,%5,%6,%7,%8,%9,%10,%11,%12,%13,%14,%15,%16,%17,%18,%19,%20,%21,%22,%23,%24,%25,%26,%27,%28,%29,%30,%31,%32,%33,%34,%35,%36,%37,%38,%39,%40,%41,%42,%43,%44,%45,%46,%47,%48,%49,%50,%51,%52,%53,%54,%55}, {%56,%57,%58,%59}, %60, p, 1, 1, %62;\n}\n"
    : "+f"(d[0]),"+f"(d[1]),"+f"(d[2]),"+f"(d[3]),"+f"(d[4]),"+f"(d[5]),"+f"(d[6]),"+f"(d[7]),"+f"(d[8]),"+f"(d[9]),"+f"(d[10]),"+f"(d[11]),"+f"(d[12]),"+f"(d[13]),"+f"(d[14]),"+f"(d[15]),"+f"(d[16]),"+f"(d[17]),"+f"(d[18]),"+f"(d[19]),"+f"(d[20]),"+f"(d[21]),"+f"(d[22]),"+f"(d[23]),"+f"(d[24]),"+f"(d[25]),"+f"(d[26]),"+f"(d[27]),"+f"(d[28]),"+f"(d[29]),"+f"(d[30]),"+f"(d[31]),"+f"(d[32]),"+f"(d[33]),"+f"(d[34]),"+f"(d[35]),"+f"(d[36]),"+f"(d[37]),"+f"(d[38]),"+f"(d[39]),"+f"(d[40]),"+f"(d[41]),"+f"(d[42]),"+f"(d[43]),"+f"(d[44]),"+f"(d[45]),"+f"(d[46]),"+f"(d[47]),"+f"(d[48]),"+f"(d[49]),"+f"(d[50]),"+f"(d[51]),"+f"(d[52]),"+f"(d[53]),"+f"(d[54]),"+f"(d[55])
    : "r"(a0), "r"(a1), "r"(a2), "r"(a3), "l"(db), "r"(sd), "n"(TB));
}

constexpr int DM = 448;
constexpr int NCTA = 128;
#define MAPPING 1
#define GRID 132
#define PINGPONG 0
#define MAP_S 4
constexpr int SPIN_LIMIT = 1 << 22;

constexpr uint32_t OFF_X = 0, OFF_Y = 114688, OFF_MISC = 229376, SMEM_BYTES = 232448;
constexpr uint32_t Y_VR = 0, Y_K = 28672, Y_KOWN = 57344, Y_VOWN = 71680, Y_Q = 86016;
constexpr uint32_t HALF = 57344;
constexpr uint32_t M_BAR = OFF_MISC;
constexpr uint32_t M_ST = OFF_MISC + 512;
constexpr uint32_t M_G = OFF_MISC + 2304;
constexpr uint32_t M_EPOCH = OFF_MISC + 3040;
enum { B_XFULL = 0, B_FULLK = 7, B_FULLV = 8, B_FULLQ, B_KRFULL, B_VRFULL, B_WOFULL, B_XCH, B_FULL = 16, B_MOD1 = 28, B_MOD2, B_WMFULL,
       B_EMPTY = 32, B_XFREE = B_EMPTY + 12, B_GEMV, B_PEER, B_DONE,
       B_PUB = 48,
       B_WMFREE = 56, B_HRDY, B_GFULL = B_HRDY + 2 };
constexpr uint32_t X_STAT = 49152;

__device__ uint32_t g_ticket;
__device__ __align__(128) uint32_t g_mod[8 * 6 * DM];
__device__ __align__(128) uint32_t g_flag[8 * 16 * 8];
__device__ __align__(128) uint32_t g_kv[17 * 8 * 2 * 3584];
__device__ __align__(128) uint32_t g_o[34 * 14336];
__device__ __align__(128) uint32_t g_x1[34 * 14336];
__device__ __align__(128) float2 g_st[34 * 8 * 64];
__device__ __align__(128) uint32_t g_h2[17 * 224 * 512];
#define PROFH(id)
#define PROFH1(id)
#define PROFC(id)

struct alignas(64) Params {
    CUtensorMap wm, xm, qkv, wo, ga, ua, gb, ub, dn;
    const bf16 *x, *c, *wqkv, *wmod, *wg, *wu, *wd, *wop;
    bf16* out;
    uint32_t zero;
};

__device__ __forceinline__ void mbar_init(uint32_t bar, int cnt) { asm volatile("mbarrier.init.shared::cta.b64 [%0], %1;" ::"r"(bar), "r"(cnt) : "memory"); }
__device__ __forceinline__ void mbar_expect_tx(uint32_t bar, uint32_t bytes) { asm volatile("mbarrier.arrive.expect_tx.shared::cta.b64 _, [%0], %1;" ::"r"(bar), "r"(bytes) : "memory"); }
__device__ __forceinline__ void mbar_arrive(uint32_t bar) { asm volatile("mbarrier.arrive.shared::cta.b64 _, [%0];" ::"r"(bar) : "memory"); }
__device__ __forceinline__ void mbar_wait(uint32_t bar, uint32_t parity) {
    uint32_t ok; int n = 0;
    do {
        asm volatile("{\n.reg .pred p;\nmbarrier.try_wait.parity.shared::cta.b64 p, [%1], %2;\nselp.u32 %0, 1, 0, p;\n}" : "=r"(ok) : "r"(bar), "r"(parity) : "memory");
        if (++n > SPIN_LIMIT) __trap();
    } while (!ok);
}
__device__ __forceinline__ void mbar_wait_cluster(uint32_t bar, uint32_t parity) {
    uint32_t ok; int n = 0;
    do {
        asm volatile("{\n.reg .pred p;\nmbarrier.try_wait.parity.acquire.cluster.shared::cta.b64 p, [%1], %2;\nselp.u32 %0, 1, 0, p;\n}" : "=r"(ok) : "r"(bar), "r"(parity) : "memory");
        if (++n > SPIN_LIMIT) __trap();
    } while (!ok);
}
__device__ __forceinline__ void warp_arrive(uint32_t bar) {
    __syncwarp();
    asm volatile("{\n.reg .pred p;\nelect.sync _|p, 0xffffffff;\n@p mbarrier.arrive.shared::cta.b64 _, [%0];\n}" ::"r"(bar) : "memory");
}
__device__ __forceinline__ int opaque(int v) { return __shfl_sync(~0u, v, 0); }
__device__ __forceinline__ int fresh_tid() { int v; asm volatile("mov.u32 %0, %%tid.x;" : "=r"(v)); return v; }
__device__ __forceinline__ void bar_sync(int id, int n) { asm volatile("bar.sync %0, %1;" ::"r"(id), "r"(n) : "memory"); }
__device__ __forceinline__ void bar_arrive(int id, int n) { asm volatile("bar.arrive %0, %1;" ::"r"(id), "r"(n) : "memory"); }
__device__ __forceinline__ void fence_async_smem() { asm volatile("fence.proxy.async.shared::cta;" ::: "memory"); }
__device__ __forceinline__ void fence_async_global() { asm volatile("fence.proxy.async.global;" ::: "memory"); }
__device__ __forceinline__ void fence_gpu() { asm volatile("fence.acq_rel.gpu;" ::: "memory"); }
__device__ __forceinline__ void tma3(uint32_t dst, const CUtensorMap* m, int c0, int c1, int c2, uint32_t bar) {
    asm volatile("cp.async.bulk.tensor.3d.shared::cluster.global.mbarrier::complete_tx::bytes [%0], [%1, {%3, %4, %5}], [%2];"
                 ::"r"(dst), "l"(m), "r"(bar), "r"(c0), "r"(c1), "r"(c2) : "memory");
}
__device__ __forceinline__ void bulk_load(uint32_t dst, const void* src, uint32_t bytes, uint32_t bar) {
    asm volatile("cp.async.bulk.shared::cluster.global.mbarrier::complete_tx::bytes [%0], [%1], %2, [%3];" ::"r"(dst), "l"(src), "r"(bytes), "r"(bar) : "memory");
}
__device__ __forceinline__ void expect_e(uint32_t bar, uint32_t bytes) {
    asm volatile("{\n.reg .pred p;\nelect.sync _|p, 0xffffffff;\n@p mbarrier.arrive.expect_tx.shared::cta.b64 _, [%0], %1;\n}" ::"r"(bar), "r"(bytes) : "memory");
}
__device__ __forceinline__ void tma3_e(uint32_t dst, const CUtensorMap* m, int c0, int c1, int c2, uint32_t bar) {
    asm volatile("{\n.reg .pred p;\nelect.sync _|p, 0xffffffff;\n@p cp.async.bulk.tensor.3d.shared::cluster.global.mbarrier::complete_tx::bytes [%0], [%1, {%3, %4, %5}], [%2];\n}"
                 ::"r"(dst), "l"(m), "r"(bar), "r"(c0), "r"(c1), "r"(c2) : "memory");
}
__device__ __forceinline__ void bulk_e(uint32_t dst, const void* src, uint32_t bytes, uint32_t bar) {
    asm volatile("{\n.reg .pred p;\nelect.sync _|p, 0xffffffff;\n@p cp.async.bulk.shared::cluster.global.mbarrier::complete_tx::bytes [%0], [%1], %2, [%3];\n}"
                 ::"r"(dst), "l"(src), "r"(bytes), "r"(bar) : "memory");
}
__device__ __forceinline__ void init_e(uint32_t bar, int cnt) {
    asm volatile("{\n.reg .pred p;\nelect.sync _|p, 0xffffffff;\n@p mbarrier.init.shared::cta.b64 [%0], %1;\n}" ::"r"(bar), "r"(cnt) : "memory");
}
__device__ __forceinline__ void l2_prefetch(const void* src, uint32_t bytes) { asm volatile("cp.async.bulk.prefetch.L2.global [%0], %1;" ::"l"(src), "r"(bytes) : "memory"); }
__device__ __forceinline__ uint32_t ld_relaxed(const uint32_t* p) { uint32_t v; asm volatile("ld.relaxed.gpu.global.u32 %0, [%1];" : "=r"(v) : "l"(p) : "memory"); return v; }
__device__ __forceinline__ void st_relaxed(uint32_t* p, uint32_t v) { asm volatile("st.relaxed.gpu.global.u32 [%0], %1;" ::"l"(p), "r"(v) : "memory"); }
__device__ __forceinline__ uint4 ld_relaxed4(const uint4* p) { uint4 v; asm volatile("ld.relaxed.gpu.global.v4.u32 {%0,%1,%2,%3}, [%4];" : "=r"(v.x), "=r"(v.y), "=r"(v.z), "=r"(v.w) : "l"(p) : "memory"); return v; }
__device__ __forceinline__ void st_relaxed4(uint4* p, uint4 v) { asm volatile("st.relaxed.gpu.global.v4.u32 [%0], {%1,%2,%3,%4};" ::"l"(p), "r"(v.x), "r"(v.y), "r"(v.z), "r"(v.w) : "memory"); }
__device__ __forceinline__ uint4 ldg_nc4(const void* p) { uint4 v; asm volatile("ld.global.nc.L1::no_allocate.v4.u32 {%0,%1,%2,%3}, [%4];" : "=r"(v.x), "=r"(v.y), "=r"(v.z), "=r"(v.w) : "l"(p)); return v; }
__device__ __forceinline__ uint32_t ldg_nc(const void* p) { uint32_t v; asm volatile("ld.global.nc.u32 %0, [%1];" : "=r"(v) : "l"(p)); return v; }
__device__ __forceinline__ uint32_t ld_acquire(const uint32_t* p) { uint32_t v; asm volatile("ld.acquire.gpu.global.u32 %0, [%1];" : "=r"(v) : "l"(p) : "memory"); return v; }
__device__ __forceinline__ uint4 lds4(uint32_t a) { uint4 v; asm volatile("ld.shared.v4.u32 {%0,%1,%2,%3}, [%4];" : "=r"(v.x), "=r"(v.y), "=r"(v.z), "=r"(v.w) : "r"(a) : "memory"); return v; }
__device__ __forceinline__ float2 lds2f(uint32_t a) { float2 v; asm volatile("ld.shared.v2.f32 {%0,%1}, [%2];" : "=f"(v.x), "=f"(v.y) : "r"(a) : "memory"); return v; }
__device__ __forceinline__ uint32_t lds1(uint32_t a) { uint32_t v; asm volatile("ld.shared.u32 %0, [%1];" : "=r"(v) : "r"(a) : "memory"); return v; }
__device__ __forceinline__ void sts4(uint32_t a, uint4 v) { asm volatile("st.shared.v4.u32 [%0], {%1,%2,%3,%4};" ::"r"(a), "r"(v.x), "r"(v.y), "r"(v.z), "r"(v.w) : "memory"); }
__device__ __forceinline__ void sts2(uint32_t a, uint32_t x, uint32_t y) { asm volatile("st.shared.v2.u32 [%0], {%1,%2};" ::"r"(a), "r"(x), "r"(y) : "memory"); }
__device__ __forceinline__ void sts1(uint32_t a, uint32_t v) { asm volatile("st.shared.u32 [%0], %1;" ::"r"(a), "r"(v) : "memory"); }
__device__ __forceinline__ void stsm4(uint32_t a, uint32_t r0, uint32_t r1, uint32_t r2, uint32_t r3) {
    asm volatile("stmatrix.sync.aligned.m8n8.x4.shared.b16 [%0], {%1,%2,%3,%4};" ::"r"(a), "r"(r0), "r"(r1), "r"(r2), "r"(r3));
}
__device__ __forceinline__ uint32_t pack2(float lo, float hi) { uint32_t r; asm("cvt.rn.bf16x2.f32 %0, %1, %2;" : "=r"(r) : "f"(hi), "f"(lo)); return r; }
__device__ __forceinline__ uint32_t pack2_relu(float lo, float hi) { uint32_t r; asm("cvt.rn.relu.bf16x2.f32 %0, %1, %2;" : "=r"(r) : "f"(hi), "f"(lo)); return r; }
__device__ __forceinline__ uint32_t hfma2(uint32_t a, uint32_t b, uint32_t c) { uint32_t r; asm("fma.rn.bf16x2 %0, %1, %2, %3;" : "=r"(r) : "r"(a), "r"(b), "r"(c)); return r; }
__device__ __forceinline__ uint32_t hmul2(uint32_t a, uint32_t b) { uint32_t r; asm("mul.rn.bf16x2 %0, %1, %2;" : "=r"(r) : "r"(a), "r"(b)); return r; }
__device__ __forceinline__ float bf_lo(uint32_t v) { return __uint_as_float(v << 16); }
__device__ __forceinline__ float bf_hi(uint32_t v) { return __uint_as_float(v & 0xFFFF0000u); }
__device__ __forceinline__ float bf_round(float v) { return bf_lo(pack2(v, 0.f)); }
__device__ __forceinline__ float ex2(float x) { float r; asm("ex2.approx.ftz.f32 %0, %1;" : "=f"(r) : "f"(x)); return r; }
__device__ __forceinline__ void mma16816(float* d, uint32_t a0, uint32_t a1, uint32_t a2, uint32_t a3, uint32_t b0, uint32_t b1) {
    asm("mma.sync.aligned.m16n8k16.row.col.f32.bf16.bf16.f32 {%0,%1,%2,%3}, {%4,%5,%6,%7}, {%8,%9}, {%0,%1,%2,%3};"
        : "+f"(d[0]), "+f"(d[1]), "+f"(d[2]), "+f"(d[3]) : "r"(a0), "r"(a1), "r"(a2), "r"(a3), "r"(b0), "r"(b1));
}
__device__ __forceinline__ void mma16816_first(float* d, uint32_t a0, uint32_t a1, uint32_t a2, uint32_t a3, uint32_t b0, uint32_t b1) {
    asm volatile("mma.sync.aligned.m16n8k16.row.col.f32.bf16.bf16.f32 {%0,%1,%2,%3}, {%4,%5,%6,%7}, {%8,%9}, {%10,%10,%10,%10};"
        : "=f"(d[0]), "=f"(d[1]), "=f"(d[2]), "=f"(d[3]) : "r"(a0), "r"(a1), "r"(a2), "r"(a3), "r"(b0), "r"(b1), "f"(0.f));
}
__device__ __forceinline__ void mma16816_v(float* d, uint32_t a0, uint32_t a1, uint32_t a2, uint32_t a3, uint32_t b0, uint32_t b1) {
    asm volatile("mma.sync.aligned.m16n8k16.row.col.f32.bf16.bf16.f32 {%0,%1,%2,%3}, {%4,%5,%6,%7}, {%8,%9}, {%0,%1,%2,%3};"
        : "+f"(d[0]), "+f"(d[1]), "+f"(d[2]), "+f"(d[3]) : "r"(a0), "r"(a1), "r"(a2), "r"(a3), "r"(b0), "r"(b1));
}
__device__ __forceinline__ void mma1688(float* d, uint32_t a0, uint32_t a1, uint32_t b0) {
    asm("mma.sync.aligned.m16n8k8.row.col.f32.bf16.bf16.f32 {%0,%1,%2,%3}, {%4,%5}, {%6}, {%0,%1,%2,%3};"
        : "+f"(d[0]), "+f"(d[1]), "+f"(d[2]), "+f"(d[3]) : "r"(a0), "r"(a1), "r"(b0));
}
__device__ __forceinline__ void ldsm4(uint32_t a, uint32_t* r) {
    asm volatile("ldmatrix.sync.aligned.m8n8.x4.shared.b16 {%0,%1,%2,%3}, [%4];" : "=r"(r[0]), "=r"(r[1]), "=r"(r[2]), "=r"(r[3]) : "r"(a));
}
__device__ __forceinline__ void ldsm4t(uint32_t a, uint32_t* r) {
    asm volatile("ldmatrix.sync.aligned.m8n8.x4.trans.shared.b16 {%0,%1,%2,%3}, [%4];" : "=r"(r[0]), "=r"(r[1]), "=r"(r[2]), "=r"(r[3]) : "r"(a));
}
__device__ __forceinline__ float rcp(float x) { float r; asm("rcp.approx.ftz.f32 %0, %1;" : "=f"(r) : "f"(x)); return r; }
__device__ __forceinline__ uint2 ld_relaxed2(const void* p) { uint2 v; asm volatile("ld.relaxed.gpu.global.v2.u32 {%0,%1}, [%2];" : "=r"(v.x), "=r"(v.y) : "l"(p) : "memory"); return v; }
__device__ __forceinline__ void st_relaxed2(void* p, uint32_t x, uint32_t y) { asm volatile("st.relaxed.gpu.global.v2.u32 [%0], {%1,%2};" ::"l"(p), "r"(max(x, 1u)), "r"(max(y, 1u)) : "memory"); }
__device__ __forceinline__ constexpr uint64_t dconst(uint32_t lbo, uint32_t sbo, uint32_t swz) {
    return ((uint64_t)(lbo >> 4) << 16) | ((uint64_t)(sbo >> 4) << 32) | ((uint64_t)swz << 62);
}
__device__ __forceinline__ uint64_t mkdesc(uint32_t addr, uint64_t c) { return c | (uint64_t)((addr & 0x3FFFF) >> 4); }
#define WG_FENCE() asm volatile("wgmma.fence.sync.aligned;" ::: "memory")
#define WG_COMMIT() asm volatile("wgmma.commit_group.sync.aligned;" ::: "memory")
#define WG_WAIT(n) asm volatile("wgmma.wait_group.sync.aligned %0;" ::"n"(n) : "memory")
template <int N> __device__ __forceinline__ void reg_fence(float* d) {
#pragma unroll
    for (int i = 0; i < N; i++) asm volatile("" : "+f"(d[i])::"memory");
}
template <int N> __device__ __forceinline__ void reg_def(float* d) {
#pragma unroll
    for (int i = 0; i < N; i++) asm volatile("" : "=f"(d[i]));
}
template <int N> __device__ __forceinline__ void reg_def(uint32_t* d) {
#pragma unroll
    for (int i = 0; i < N; i++) asm volatile("" : "=r"(d[i]));
}
__device__ __forceinline__ bool is_unset(uint4 v) { return min(min(v.x, v.y), min(v.z, v.w)) == 0u; }
__device__ __forceinline__ uint4 nz4(uint32_t a, uint32_t b, uint32_t c, uint32_t d) { return make_uint4(max(a, 1u), max(b, 1u), max(c, 1u), max(d, 1u)); }
__device__ __forceinline__ void wait_flag(const uint32_t* p, uint32_t target) {
    int n = 0;
    while ((int)(ld_acquire(p) - target) < 0) { if (++n > SPIN_LIMIT) __trap(); }
}
__device__ __forceinline__ float silu_bf(uint32_t cbits) {
    const float c = __uint_as_float(cbits << 16);
    return bf_round(__fdividef(c, 1.f + fminf(ex2(-1.4426950408889634f * c), 1e30f)));
}
__device__ __forceinline__ void gemv_part(uint32_t wmbuf, int npanel, int wp, int lane) {
    const uint32_t wa = wmbuf + wp * 512 + (8 * (lane >> 4) + (lane & 7)) * 32 + ((lane >> 3) & 1) * 16;
    uint2 B[4];
#pragma unroll
    for (int i = 0; i < 4; i++) { const float2 v = lds2f(wmbuf + 28672 + (wp + 8 * i) * 32 + (lane & 3) * 8); B[i] = make_uint2(__float_as_uint(v.x), __float_as_uint(v.y)); }
#pragma unroll 1
    for (int pn = 0; pn < npanel; pn++) {
        float d[4] = {};
        uint32_t A[16];
#pragma unroll
        for (int i = 0; i < 4; i++) ldsm4t(wa + pn * 14336 + (i < 3 || wp < 4 ? i : 0) * 4096, A + 4 * i);
#pragma unroll
        for (int i = 0; i < 4; i++) mma16816(d, A[4 * i], A[4 * i + 1], A[4 * i + 2], A[4 * i + 3], B[i].x, B[i].y);
        if ((lane & 3) == 0) {
            sts1(wmbuf + 29696 + (wp * 32 + pn * 16 + (lane >> 2)) * 4, __float_as_uint(d[0]));
            sts1(wmbuf + 29696 + (wp * 32 + pn * 16 + 8 + (lane >> 2)) * 4, __float_as_uint(d[2]));
        }
    }
}
__device__ __forceinline__ void ln_coeffs(float mean, float msq, uint32_t& r2, uint32_t& n2) {
    const float rs = bf_round(rsqrtf(fmaxf(msq - mean * mean, 0.f) + 1e-5f));
    r2 = pack2(rs, rs);
    n2 = pack2(-mean * rs, -mean * rs);
}

__global__ void __cluster_dims__(2, 1, 1) __launch_bounds__(384, 1) fused_block_kernel(const __grid_constant__ Params p) {
    extern __shared__ __align__(1024) unsigned char smem[];
    const uint32_t sb = (uint32_t)__cvta_generic_to_shared(smem);
    const int tid = threadIdx.x, lane = tid & 31, warp = __shfl_sync(~0u, tid >> 5, 0);
    const int m = blockIdx.x >> 1;
#define kh (j & 1)
    int r, nq;
    {
        int g, i;
        if (m < MAP_S) { g = m < 4 ? 15 : 16; i = m & 3; }
        else if (m < MAP_S + 32) { g = (m - MAP_S) & 7; i = (m - MAP_S) >> 3; }
        else if (m < MAP_S + 60) { i = (m - MAP_S - 32) / 7; g = 8 + (m - MAP_S - 32) - 7 * i; }
        else { g = 16; i = m & 3; }
        r = g; nq = i;
    }
    const int j = opaque(2 * nq + (blockIdx.x & 1)), b = 8 * r + j, fs = 4 * kh + nq;
    const uint32_t sc = r == 16;
#define BAR(i) (sb + M_BAR + 8 * (i))
    if (lane == 0 && warp < 9 && warp != 6 && warp != 7) {
        const int i0 = warp == 8 ? 0 : 8 + 8 * warp, cnt = warp == 0 || warp == 8 ? 1 : warp < 3 ? 2 : 8;
#pragma unroll
        for (int k = 0; k < 8; k++) if (i0 + k != B_WMFULL) mbar_init(BAR(i0 + k), cnt);
        asm volatile("fence.mbarrier_init.release.cluster;" ::: "memory");
        fence_async_smem();
    }

    if (warp < 8) {
        const int w = warp >> 2, wi = warp & 3;
#define COORDS const int t = fresh_tid() & 127, lane = t & 31, q = lane & 3, lr = lane >> 2, ra = 64 * w + 16 * wi + lr; \
        const uint32_t lx = (lane >> 4) ^ (lane & 7), mrow = (64 * w + 16 * wi + ((lane >> 3) & 1) * 8 + (lane & 7)) * 128; \
        (void)q; (void)lr; (void)ra; (void)lx; (void)mrow;
        const int sid = 2 * (j & 3) + w;
#define RUN(k) (!sc || sid == (k))
#define WAIT(i, par) mbar_wait(BAR(i), (par) | sc)
        constexpr uint64_t DB128 = dconst(4096, 1024, 1);
        bar_arrive(9, 384);
        bar_sync(0, 384);
        asm volatile("barrier.cluster.arrive.relaxed.aligned;" ::: "memory");
        asm volatile("setmaxnreg.inc.sync.aligned.u32 224;");
        PROFC(0);
        uint32_t xr[16];
        {
            COORDS
            uint32_t h[112];
            if (RUN(0)) {
                float ds[4] = {}, da[2][4] = {}, db[2][4] = {};
                const uint32_t ONE2 = 0x3F803F80u;
                if (kh == 0) { WAIT(B_WMFULL, 0); gemv_part(sb + OFF_Y + HALF, 1, warp, lane); warp_arrive(BAR(B_GEMV)); }
#pragma unroll
                for (int kb = 0; kb < 7; kb++) {
                    WAIT(B_XFULL + kb, 0);
#pragma unroll
                    for (int k4 = 0; k4 < 4; k4++) ldsm4(sb + OFF_X + mrow + kb * 16384 + (((2 * k4) ^ lx) << 4), h + 16 * kb + 4 * k4);
#pragma unroll
                    for (int k4 = 0; k4 < 4; k4++) {
                        const uint32_t* f = h + 16 * kb + 4 * k4;
                        mma16816(ds, f[0], f[1], f[2], f[3], ONE2, ONE2);
                        mma1688(da[0], f[0], f[1], f[0]); mma1688(db[0], f[0], f[1], f[1]);
                        mma1688(da[1], f[2], f[3], f[2]); mma1688(db[1], f[2], f[3], f[3]);
                    }
                }
#pragma unroll
                for (int i = 0; i < 4; i++) {
                    const int ch = 7 * j + 2 * i + (lane >> 4);
                    ldsm4(sb + OFF_X + mrow + (ch >> 3) * 16384 + (((ch ^ lane) & 7) << 4), xr + 4 * i);
                }
                warp_arrive(BAR(B_XFREE));
                PROFC(27);
                float qa = (lr & 1) ? da[0][1] + da[1][1] : da[0][0] + da[1][0];
                float qb = (lr & 1) ? db[0][3] + db[1][3] : db[0][2] + db[1][2];
                const int src = (lane & ~3) | (lr >> 1);
                qa = __shfl_sync(~0u, qa, src);
                qb = __shfl_sync(~0u, qb, src);
                uint32_t ra2, na2, rb2, nb2;
                ln_coeffs(ds[0] * (1.f / DM), qa * (1.f / DM), ra2, na2);
                ln_coeffs(ds[2] * (1.f / DM), qb * (1.f / DM), rb2, nb2);
#pragma unroll
                for (int i = 0; i < 112; i += 2) { h[i] = hfma2(h[i], ra2, na2); h[i + 1] = hfma2(h[i + 1], rb2, nb2); }
                if (kh == 1) { WAIT(B_WMFULL, 0); gemv_part(sb + OFF_Y + HALF, 2, warp, lane); warp_arrive(BAR(B_GEMV)); }
            } else { reg_def<112>(h); reg_def<16>(xr); }
            PROFC(1);
            if (RUN(1)) {
                float ak[28], av[28], aq[28];
                uint32_t kp[14], vp[14];
                const uint64_t bk0 = mkdesc(sb + OFF_Y, DB128) + kh, bv0 = mkdesc(sb + OFF_Y + HALF, DB128) + kh, bq0 = mkdesc(sb + OFF_X, DB128) + kh;
                uint32_t* kvg = g_kv + (size_t)(b * 2) * 3584 + (8 * w + 2 * wi) * 224 + lane;
                WAIT(B_FULLK, 0);
                WAIT(B_MOD1, 0);
                PROFC(2);
                reg_def<28>(ak);
#pragma unroll
                for (int g4 = 0; g4 < 4; g4++) {
#pragma unroll
                    for (int ks = 7 * g4; ks < 7 * g4 + 7; ks++) {
                        const uint4 st = *(const uint4*)(smem + M_ST + ks * 64 + q * 16);
                        h[4 * ks] = hfma2(h[4 * ks], st.x, st.y); h[4 * ks + 1] = hfma2(h[4 * ks + 1], st.x, st.y);
                        h[4 * ks + 2] = hfma2(h[4 * ks + 2], st.z, st.w); h[4 * ks + 3] = hfma2(h[4 * ks + 3], st.z, st.w);
                    }
                    WG_FENCE();
#pragma unroll
                    for (int ks = 7 * g4; ks < 7 * g4 + 7; ks++) wgmma_rs_56<1>(ak, h[4 * ks], h[4 * ks + 1], h[4 * ks + 2], h[4 * ks + 3], bk0 + ks * 128, ks != 0);
                }
                WG_COMMIT();
                PROFC(3);
                WAIT(B_FULLV, 0);
                reg_def<28>(av);
                WG_FENCE();
#pragma unroll
                for (int ks = 0; ks < 8; ks++) wgmma_rs_56<1>(av, h[4 * ks], h[4 * ks + 1], h[4 * ks + 2], h[4 * ks + 3], bv0 + ks * 128, ks != 0);
                WG_COMMIT();
                WG_WAIT(1);
                reg_fence<28>(ak);
#pragma unroll
                for (int g = 0; g < 7; g++) {
                    kp[2 * g] = pack2(ak[4 * g], ak[4 * g + 1]); kp[2 * g + 1] = pack2(ak[4 * g + 2], ak[4 * g + 3]);
                    kvg[g * 32] = kp[2 * g]; kvg[224 + g * 32] = kp[2 * g + 1];
                }
                warp_arrive(BAR(B_PUB));
                PROFC(4);
                WG_FENCE();
#pragma unroll
                for (int ks = 8; ks < 28; ks++) wgmma_rs_56<1>(av, h[4 * ks], h[4 * ks + 1], h[4 * ks + 2], h[4 * ks + 3], bv0 + ks * 128, 1);
                WG_COMMIT();
                WAIT(B_FULLQ, 0);
                reg_def<28>(aq);
                WG_FENCE();
#pragma unroll
                for (int ks = 0; ks < 8; ks++) wgmma_rs_56<1>(aq, h[4 * ks], h[4 * ks + 1], h[4 * ks + 2], h[4 * ks + 3], bq0 + ks * 128, ks != 0);
                WG_COMMIT();
                WG_WAIT(1);
                reg_fence<28>(av);
#pragma unroll
                for (int g = 0; g < 7; g++) {
                    vp[2 * g] = pack2(av[4 * g], av[4 * g + 1]); vp[2 * g + 1] = pack2(av[4 * g + 2], av[4 * g + 3]);
                    kvg[3584 + g * 32] = vp[2 * g]; kvg[3584 + 224 + g * 32] = vp[2 * g + 1];
                }
                warp_arrive(BAR(B_PUB + 1));
                PROFC(5);
                WG_FENCE();
#pragma unroll
                for (int ks = 8; ks < 28; ks++) wgmma_rs_56<1>(aq, h[4 * ks], h[4 * ks + 1], h[4 * ks + 2], h[4 * ks + 3], bq0 + ks * 128, 1);
                WG_COMMIT();
                WAIT(B_PUB + 1, 0);
                const uint32_t ko = sb + OFF_Y + Y_KOWN + (8 * w + 2 * wi) * 896 + lane * 4;
                const uint32_t qo = sb + OFF_Y + Y_Q + (8 * w + 2 * wi) * 1024 + lane * 4;
#pragma unroll
                for (int g = 0; g < 7; g++) {
                    sts1(ko + g * 128, kp[2 * g]); sts1(ko + 896 + g * 128, kp[2 * g + 1]);
                    sts1(ko + (Y_VOWN - Y_KOWN) + g * 128, vp[2 * g]); sts1(ko + (Y_VOWN - Y_KOWN) + 896 + g * 128, vp[2 * g + 1]);
                }
                WG_WAIT(0);
                reg_fence<28>(aq);
                __syncwarp();
                if (lane < 3 && w == 1) mbar_arrive(BAR(B_EMPTY + lane));
#pragma unroll
                for (int g = 0; g < 7; g++) {
                    const uint32_t q0 = pack2(aq[4 * g], aq[4 * g + 1]), q1 = pack2(aq[4 * g + 2], aq[4 * g + 3]);
                    if (g == 3) {
                        sts1(qo + 3 * 128, q < 2 ? q0 : 0u); sts1(qo + 1024 + 3 * 128, q < 2 ? q1 : 0u);
                        sts1(qo + 4 * 128, q < 2 ? 0u : q0); sts1(qo + 1024 + 4 * 128, q < 2 ? 0u : q1);
                    } else {
                        const int ch = g < 3 ? g : g + 1;
                        sts1(qo + ch * 128, q0); sts1(qo + 1024 + ch * 128, q1);
                    }
                }
                if (!sc) bar_sync(3, 256);
            }
        }
        PROFC(6);
        WAIT(B_KRFULL, 0);
        PROFC(7);
        if (RUN(2)) {
#pragma unroll 1
            for (int hf = sc; hf < 2; hf++) {
                COORDS
                float s[136];
                float na = 0.f, nb = 0.f;
                const float CS = 0.18898223650461361f * 1.4426950408889634f;
                const int kg0 = 8 * hf + 2 * wi;
                const int pmin = 16 - 8 * r - 4 * hf - wi;
                const float NEG = __int_as_float(0xFF800000);
                {
                    uint32_t F[8];
                    const uint32_t qa = sb + OFF_Y + Y_Q + (kg0 + ((lane >> 3) & 1)) * 1024 + (4 * w + (lane >> 4)) * 128 + (lane & 7) * 16;
                    ldsm4(qa, F); ldsm4(qa + 256, F + 4);
                    uint32_t ka = sb + OFF_Y + Y_K + kg0 * 896 + (3 * w + (lane >> 3)) * 128 + (lane & 7) * 16;
#pragma unroll
                    for (int g = 0; g < 34; g++) {
                        uint32_t B[4];
                        if (g >= 12 && g % 4 == 0) ka += __float_as_uint(s[4 * (g - 12)]) & p.zero;
                        ldsm4(ka + g * 896, B);
                        mma16816_first(s + 4 * g, F[0], F[1], F[2], F[3], B[0], B[1]);
                        mma16816_v(s + 4 * g, F[4], F[5], F[6], F[7], B[2], B[3]);
                    }
                    const bool c0 = 2 * q > lr, c1 = 2 * q + 1 > lr;
                    if (!c0) { s[0] = NEG; s[6] = NEG; }
                    if (!c1) { s[1] = NEG; s[7] = NEG; }
                    s[2] = NEG; s[3] = NEG;
                    if (c0) { s[128] = NEG; s[134] = NEG; }
                    if (c1) { s[129] = NEG; s[135] = NEG; }
                    s[132] = NEG; s[133] = NEG;
                    float ma = NEG, mb = NEG;
#pragma unroll
                    for (int pp = 0; pp < 17; pp++) {
                        const float* e = s + 8 * pp;
                        const float bias = pp < pmin ? NEG : 0.f;
                        ma = fmaxf(ma, fmaxf(fmaxf(e[0], e[1]), fmaxf(e[4], e[5])) + bias);
                        mb = fmaxf(mb, fmaxf(fmaxf(e[2], e[3]), fmaxf(e[6], e[7])) + bias);
                    }
                    ma = fmaxf(ma, __shfl_xor_sync(~0u, ma, 1)); mb = fmaxf(mb, __shfl_xor_sync(~0u, mb, 1));
                    ma = fmaxf(ma, __shfl_xor_sync(~0u, ma, 2)); mb = fmaxf(mb, __shfl_xor_sync(~0u, mb, 2));
                    na = -ma * CS; nb = -mb * CS;
                }
                PROFC(8 + 3 * hf);
                {
                    if (hf == 0) mbar_wait(BAR(B_VRFULL), 0);
                    float o[16] = {}, rs[4] = {};
                    const uint32_t va = sb + OFF_Y + Y_VR + (kg0 + ((lane >> 3) & 1)) * 896 + (3 * w + (lane >> 4)) * 128 + (lane & 7) * 16;
#pragma unroll
                    for (int pp = 0; pp < 17; pp++) {
                        uint32_t B[8];
                        const uint32_t v = va + pp * 1792 + (pp == 16 || (pp >= 9 && kg0 + 2 * pp >= 32) ? Y_VOWN - 32 * 896 : 0);
                        ldsm4t(v, B); ldsm4t(v + 256, B + 4);
                        float e[8];
#pragma unroll
                        for (int i = 0; i < 8; i++) e[i] = ex2(fmaf(s[8 * pp + i], CS, ((i & 2) ? nb : na) + (pp < pmin ? NEG : 0.f)));
                        const uint32_t p0 = pack2(e[0], e[1]), p1 = pack2(e[2], e[3]), p2 = pack2(e[4], e[5]), p3 = pack2(e[6], e[7]);
                        mma16816(rs, p0, p1, p2, p3, 0x3F803F80u, 0x3F803F80u);
#pragma unroll
                        for (int g = 0; g < 4; g++) mma16816(o + 4 * g, p0, p1, p2, p3, B[2 * g], B[2 * g + 1]);
                    }
                    PROFC(9 + 3 * hf);
                    const float ia = rcp(rs[0]), ib = rcp(rs[2]);
                    uint32_t* og = g_o + (size_t)(2 * r + hf) * 14336 + (7 * j + 3 * w) * 256 + wi * 64 + lane;
#pragma unroll
                    for (int g = 0; g < 4; g++) {
                        if ((g == 3 - 3 * w) ? ((q >> 1) == w) : true) {
                            og[g * 256] = pack2(o[4 * g] * ia, o[4 * g + 1] * ia);
                            og[g * 256 + 32] = pack2(o[4 * g + 2] * ib, o[4 * g + 3] * ib);
                        }
                    }
                    warp_arrive(BAR(B_PUB + 2 + hf));
                    PROFC(10 + 3 * hf);
                }
            }
        }
        uint32_t x1p[14];
        COORDS
        constexpr uint64_t DT = dconst(1024, 128, 0);
        if (RUN(4)) {
            float ac[28];
            const uint64_t ad = mkdesc(sb + (w ? OFF_Y + HALF : OFF_X), DT), bd = mkdesc(sb + OFF_X + HALF, DB128) + kh;
            WAIT(B_WOFULL, 0);
            WAIT(B_MOD2, 0);
            WAIT(B_GFULL + w, 0);
            PROFC(28);
            reg_def<28>(ac);
#pragma unroll 1
            for (int u = 0; u < 4; u++) {
                WG_FENCE();
#pragma unroll
                for (int i = 0; i < 7; i++) wgmma_ss_56<1>(ac, ad + (7 * u + i) * 128, bd + (7 * u + i) * 128, (u | i) != 0);
            }
            WG_COMMIT();
            WG_WAIT(0);
            reg_fence<28>(ac);
            PROFC(14);
            __syncwarp();
            if (lane < 3) mbar_arrive(BAR(B_EMPTY + 4 + lane));
            float s1a = 0.f, s2a = 0.f, s1b = 0.f, s2b = 0.f;
            uint32_t* xo = g_x1 + (size_t)(2 * r + w) * 14336 + 7 * j * 256 + wi * 64 + lane;
#pragma unroll
            for (int g = 0; g < 7; g++) {
                const float2 ga = *(const float2*)(smem + M_G + (8 * g + 2 * q) * 4);
                x1p[2 * g] = pack2(fmaf(ga.x, ac[4 * g], bf_lo(xr[2 * g])), fmaf(ga.y, ac[4 * g + 1], bf_hi(xr[2 * g])));
                x1p[2 * g + 1] = pack2(fmaf(ga.x, ac[4 * g + 2], bf_lo(xr[2 * g + 1])), fmaf(ga.y, ac[4 * g + 3], bf_hi(xr[2 * g + 1])));
                xo[g * 256] = x1p[2 * g]; xo[g * 256 + 32] = x1p[2 * g + 1];
                const float u0 = bf_lo(x1p[2 * g]), u1 = bf_hi(x1p[2 * g]), u2 = bf_lo(x1p[2 * g + 1]), u3 = bf_hi(x1p[2 * g + 1]);
                s1a += u0 + u1; s2a += u0 * u0 + u1 * u1; s1b += u2 + u3; s2b += u2 * u2 + u3 * u3;
            }
            float ka = (q & 1) ? s2a : s1a, kb2 = (q & 1) ? s2b : s1b;
            ka += __shfl_xor_sync(~0u, (q & 1) ? s1a : s2a, 1); kb2 += __shfl_xor_sync(~0u, (q & 1) ? s1b : s2b, 1);
            const float kk = ((q & 2) ? kb2 : ka) + __shfl_xor_sync(~0u, (q & 2) ? ka : kb2, 2);
            ((float*)g_st)[(((2 * r + w) * 8 + j) * 64 + 16 * wi + lr + 4 * (q & 2)) * 2 + (q & 1)] = kk;
            __syncwarp();
            if (lane < 2) mbar_arrive(BAR(B_PUB + 4 + w));
        } else reg_def<14>(x1p);
        PROFC(15);
        if (RUN(5)) {
            WAIT(B_GFULL + 2 + w, 0);
            PROFC(16);
            if (lane < 3 && w == 0) mbar_arrive(BAR(B_EMPTY + lane));
            float2 sa = make_float2(0.f, 0.f), sbb = sa;
#pragma unroll
            for (int jj = 0; jj < 8; jj++) {
                const float2 u = lds2f(sb + OFF_X + X_STAT + w * 4096 + (jj * 64 + 16 * wi + lr) * 8), v = lds2f(sb + OFF_X + X_STAT + w * 4096 + (jj * 64 + 16 * wi + lr + 8) * 8);
                sa.x += u.x; sa.y += u.y; sbb.x += v.x; sbb.y += v.y;
            }
            warp_arrive(BAR(B_EMPTY + 3));
            uint32_t ra2, na2, rb2, nb2;
            ln_coeffs(sa.x * (1.f / DM), sa.y * (1.f / DM), ra2, na2);
            ln_coeffs(sbb.x * (1.f / DM), sbb.y * (1.f / DM), rb2, nb2);
            const uint32_t ha = sb + OFF_Y + w * HALF + (lane >> 4) * 1024 + (2 * wi + ((lane >> 3) & 1)) * 128 + (lane & 7) * 16;
#pragma unroll 1
            for (int k0 = 0; k0 < 28; k0 += 7) {
                uint32_t f[28];
                uint4 st[7];
#pragma unroll
                for (int i = 0; i < 7; i++) { ldsm4(ha + (k0 + i) * 2048, f + 4 * i); st[i] = lds4(sb + M_ST + (k0 + i) * 64 + q * 16); }
#pragma unroll
                for (int i = 0; i < 7; i++)
                    stsm4(ha + (k0 + i) * 2048, hfma2(hfma2(f[4 * i], ra2, na2), st[i].x, st[i].y), hfma2(hfma2(f[4 * i + 1], rb2, nb2), st[i].x, st[i].y),
                          hfma2(hfma2(f[4 * i + 2], ra2, na2), st[i].z, st[i].w), hfma2(hfma2(f[4 * i + 3], rb2, nb2), st[i].z, st[i].w));
            }
            fence_async_smem();
            bar_sync(1 + w, 128);
        }
        PROFC(17);
        uint32_t h2a[32], h2b[24];
        if (RUN(6)) {
            const int fa = 224 * fs + ((fs & 1) ? 96 : 0), fb = 224 * fs + ((fs & 1) ? 0 : 128);
            uint32_t* h2g = g_h2 + (size_t)r * (224 * 512) + (8 * w + 2 * wi) * 32 + lane;
            const uint64_t a0 = mkdesc(sb + OFF_Y + w * HALF, DT);
            const int s0 = sc ? 12 : 0;
            {
                float ac[128];
                reg_def<128>(ac);
                int sl = 0, prev = 0;
#pragma unroll 1
                for (int s = s0; s < 14; s++) {
                    WAIT(B_FULL + sl, s >= 7);
                    const uint64_t ad = a0 + s * 256, bd = mkdesc(sb + OFF_X + sl * 16384, DB128);
                    WG_FENCE();
                    wgmma_ss_256<1>(ac, ad, bd, s != 0);
                    wgmma_ss_256<1>(ac, ad + 128, bd + 128, 1);
                    WG_COMMIT();
                    if (s > 0) { WG_WAIT(1); warp_arrive(BAR(B_EMPTY + prev)); }
                    prev = sl; sl = sl == 6 ? 0 : sl + 1;
                }
                WG_WAIT(0);
                reg_fence<128>(ac);
                warp_arrive(BAR(B_EMPTY + 6));
                PROFC(18);
#pragma unroll
                for (int g = 0; g < 16; g++) {
                    h2a[2 * g] = hmul2(pack2_relu(ac[4 * g], ac[4 * g + 1]), pack2(ac[64 + 4 * g], ac[64 + 4 * g + 1]));
                    h2a[2 * g + 1] = hmul2(pack2_relu(ac[4 * g + 2], ac[4 * g + 3]), pack2(ac[64 + 4 * g + 2], ac[64 + 4 * g + 3]));
                    h2g[(fa / 8 + g) * 512] = h2a[2 * g]; h2g[(fa / 8 + g) * 512 + 32] = h2a[2 * g + 1];
                }
                warp_arrive(BAR(B_PUB + 6));
            }
            PROFC(19);
            {
                float ac[96];
                reg_def<96>(ac);
                int sl = 0, prev = 0;
#pragma unroll 1
                for (int s = s0; s < 14; s++) {
                    WAIT(B_FULL + sl, s >= 7);
                    const uint64_t ad = a0 + s * 256, bd = mkdesc(sb + OFF_X + sl * 16384, dconst(2048, 512, 2));
                    WG_FENCE();
                    wgmma_ss_192<1>(ac, ad, bd, s != 0);
                    wgmma_ss_192<1>(ac, ad + 128, bd + 64, 1);
                    WG_COMMIT();
                    if (s > 0) { WG_WAIT(1); warp_arrive(BAR(B_EMPTY + prev)); }
                    prev = sl; sl = sl == 6 ? 0 : sl + 1;
                }
                WG_WAIT(0);
                reg_fence<96>(ac);
                __syncwarp();
                if (lane < 6) mbar_arrive(BAR(B_EMPTY + 6 + lane));
                asm volatile("barrier.cluster.wait.aligned;" ::: "memory");
                if (lane == 0 && !sc) {
                    uint32_t rb;
                    asm volatile("mapa.shared::cluster.u32 %0, %1, %2;" : "=r"(rb) : "r"(BAR(B_PEER)), "r"(kh ^ 1));
                    asm volatile("mbarrier.arrive.relaxed.cluster.shared::cluster.b64 _, [%0];" ::"r"(rb) : "memory");
                }
                PROFC(20);
#pragma unroll
                for (int g = 0; g < 12; g++) {
                    h2b[2 * g] = hmul2(pack2_relu(ac[4 * g], ac[4 * g + 1]), pack2(ac[48 + 4 * g], ac[48 + 4 * g + 1]));
                    h2b[2 * g + 1] = hmul2(pack2_relu(ac[4 * g + 2], ac[4 * g + 3]), pack2(ac[48 + 4 * g + 2], ac[48 + 4 * g + 3]));
                    h2g[(fb / 8 + g) * 512] = h2b[2 * g]; h2g[(fb / 8 + g) * 512 + 32] = h2b[2 * g + 1];
                }
                warp_arrive(BAR(B_PUB + 7));
            }
        } else { reg_def<32>(h2a); reg_def<24>(h2b); }
        PROFC(21);
        if (RUN(7)) {
            float ac[56];
            reg_def<56>(ac);
            constexpr uint64_t DAN = dconst(2048, 128, 0);
#pragma unroll 1
            for (int u = 0; u < 12; u++) {
                WAIT(B_FULL + u, 0);
                const uint32_t sl = sb + u * 16384;
                const uint64_t ad = mkdesc(sl + 8192 + w * 1024, DAN), bd = mkdesc(sl, DB128);
                WG_FENCE();
                wgmma_ss_112<1>(ac, ad, bd, u != 0);
                wgmma_ss_112<1>(ac, ad + 256, bd + 128, 1);
                WG_COMMIT();
                if (u > 0) { WG_WAIT(1); warp_arrive(BAR(B_EMPTY + u - 1)); }
            }
            PROFC(22);
#pragma unroll
            for (int u = 0; u < 7; u++) {
                WAIT(B_FULL + u, 1);
                const uint64_t bd = mkdesc(sb + u * 16384, DB128);
                const uint32_t* hh = u < 4 ? h2a + 8 * u : h2b + 8 * (u - 4);
                WG_FENCE();
                wgmma_rs_112<1>(ac, hh[0], hh[1], hh[2], hh[3], bd, 1);
                wgmma_rs_112<1>(ac, hh[4], hh[5], hh[6], hh[7], bd + 128, 1);
                WG_COMMIT();
                if (u > 0 && u < 5) { WG_WAIT(1); warp_arrive(BAR(B_EMPTY + u - 1)); }
                if (u == 0) { WG_WAIT(1); warp_arrive(BAR(B_EMPTY + 11)); }
            }
            PROFC(23);
#pragma unroll 1
            for (int u = 7; u < 16; u++) {
                const int sli = u < 12 ? u : u - 12;
                WAIT(B_FULL + sli, u < 12);
                const uint32_t sl = sb + sli * 16384;
                const uint64_t ad = mkdesc(sl + 8192 + w * 1024, DAN), bd = mkdesc(sl, DB128);
                WG_FENCE();
                wgmma_ss_112<1>(ac, ad, bd, 1);
                wgmma_ss_112<1>(ac, ad + 256, bd + 128, 1);
                WG_COMMIT();
            }
            mbar_wait_cluster(BAR(B_PEER), sc);
            WG_WAIT(0);
            reg_fence<56>(ac);
            PROFC(24);
            uint32_t rdst, rbar;
            asm volatile("mapa.shared::cluster.u32 %0, %1, %2;" : "=r"(rdst) : "r"(sb + OFF_Y + (5 + w) * 16384 + t * 16), "r"(kh ^ 1 ^ sc));
            asm volatile("mapa.shared::cluster.u32 %0, %1, %2;" : "=r"(rbar) : "r"(BAR(B_XCH + w)), "r"(kh ^ 1 ^ sc));
#pragma unroll
            for (int g = 0; g < 7; g++) {
                const float v0 = kh ? ac[4 * g] : ac[28 + 4 * g], v1 = kh ? ac[4 * g + 1] : ac[28 + 4 * g + 1];
                const float v2 = kh ? ac[4 * g + 2] : ac[28 + 4 * g + 2], v3 = kh ? ac[4 * g + 3] : ac[28 + 4 * g + 3];
                if (!sc) asm volatile("st.async.shared::cluster.mbarrier::complete_tx::bytes.v4.f32 [%0], {%1,%2,%3,%4}, [%5];"
                             ::"r"(rdst + g * 2048), "f"(v0), "f"(v1), "f"(v2), "f"(v3), "r"(rbar) : "memory");
            }
            mbar_wait_cluster(BAR(B_XCH + w), sc);
            PROFC(25);
            bf16* og = (sc ? (bf16*)(g_h2 + 16 * 224 * 512) : p.out + (size_t)128 * r * DM) + (size_t)ra * DM + 56 * j + 2 * q;
#pragma unroll
            for (int g = 0; g < 7; g++) {
                const uint4 rv = *(const uint4*)(smem + OFF_Y + (5 + w) * 16384 + t * 16 + g * 2048);
                const float2 gb = *(const float2*)(smem + M_G + 224 + (8 * g + 2 * q) * 4);
                const float v0 = (kh ? ac[28 + 4 * g] : ac[4 * g]) + __uint_as_float(rv.x), v1 = (kh ? ac[28 + 4 * g + 1] : ac[4 * g + 1]) + __uint_as_float(rv.y);
                const float v2 = (kh ? ac[28 + 4 * g + 2] : ac[4 * g + 2]) + __uint_as_float(rv.z), v3 = (kh ? ac[28 + 4 * g + 3] : ac[4 * g + 3]) + __uint_as_float(rv.w);
                *(uint32_t*)(og + 8 * g) = pack2(fmaf(gb.x, v0, bf_lo(x1p[2 * g])), fmaf(gb.y, v1, bf_hi(x1p[2 * g])));
                *(uint32_t*)(og + 8 * DM + 8 * g) = pack2(fmaf(gb.x, v2, bf_lo(x1p[2 * g + 1])), fmaf(gb.y, v3, bf_hi(x1p[2 * g + 1])));
            }
        }
        PROFC(26);
        warp_arrive(BAR(B_DONE));
    } else {
        const int lane = fresh_tid() & 31;
        const bool early = kh == 0, gemv = r < 14;
        const int mcol = early ? 16 * (4 * r + nq) : 2 * DM + 32 * (4 * r + nq);
        const uint32_t wmbuf = sb + OFF_Y + HALF;
        const int fa = 224 * fs + ((fs & 1) ? 96 : 0), fb = 224 * fs + ((fs & 1) ? 0 : 128);
        asm volatile("setmaxnreg.dec.sync.aligned.u32 56;");
        if (warp == 9) {
#pragma unroll
            for (int i = 56; i < 63; i++) init_e(BAR(i), 1);
            fence_async_smem();
        }
        if (warp == 8) { init_e(BAR(B_WMFULL), 2); fence_async_smem(); }
        bar_arrive(0, 384);
        asm volatile("barrier.cluster.arrive.relaxed.aligned;" ::: "memory");
        uint32_t target = 0;
        if (warp == 8) {
            if (!sc) {
                expect_e(BAR(B_WMFULL), gemv ? 28672 >> early : 0);
                if (early && gemv) { tma3_e(wmbuf, &p.wm, mcol, 0, 0, BAR(B_WMFULL)); tma3_e(wmbuf + 7168, &p.wm, mcol, 224, 0, BAR(B_WMFULL)); }
#pragma unroll 1
                for (int kb = 0; kb < 7; kb++) {
                    expect_e(BAR(B_XFULL + kb), 16384);
                    tma3_e(sb + OFF_X + kb * 16384, &p.xm, 64 * kb, 128 * r, 0, BAR(B_XFULL + kb));
                }
            }
            PROFH(0);
#pragma unroll 1
            for (int mt = 0; mt < 4; mt++) {
                if (mt == 1) {
                    if (!early && gemv) {
#pragma unroll 1
                        for (int k = 0; k < 4; k++) tma3_e(wmbuf + k * 7168, &p.wm, mcol + (k >> 1) * 16, (k & 1) * 224, 0, BAR(B_WMFULL));
                    }
                    bar_sync(9, 384);
                    if (sc) return;
                    mbar_wait(BAR(B_MOD1), 0);
                    mbar_wait(BAR(B_WMFREE), 0);
                }
                if (mt == 2) mbar_wait(BAR(B_XFREE), 0);
                if (mt == 3) mbar_wait(BAR(B_VRFULL), 0);
                const uint32_t bar = BAR(mt == 3 ? B_WOFULL : B_FULLK + mt), dst = sb + (mt < 2 ? OFF_Y : OFF_X) + (mt & 1) * HALF;
                const int c0 = (mt < 2 ? DM + DM * mt : 0) + 56 * j - 8 * kh;
                if (!sc) {
                    expect_e(bar, HALF);
                    tma3_e(dst, mt == 3 ? &p.wo : &p.qkv, c0, 0, 0, bar);
                    tma3_e(dst + HALF / 2, mt == 3 ? &p.wo : &p.qkv, c0, 224, 0, bar);
                }
                if (mt & 1) PROFH(1 + (mt >> 1));
            }
            expect_e(BAR(B_XCH), 14336);
            expect_e(BAR(B_XCH + 1), 14336);
        } else {
            if (warp == 10 && lane == 0 && !sc) {
                const uint32_t ticket = atomicAdd(&g_ticket, 1u);
                l2_prefetch((const char*)p.wqkv + (size_t)b * 9408, 9408);
                sts1(sb + M_EPOCH, ticket / NCTA);
            }
            if (warp == 11) {
#pragma unroll
                for (int i = 0; i < 8; i++) {
                    const int wd = lane + 32 * i;
                    const uint32_t cb = i < 7 ? __ldg((const uint32_t*)p.c + wd) : 0u;
                    sts1(wmbuf + 28672 + (wd >> 3) * 32 + (wd & 3) * 8 + (wd & 4), pack2(silu_bf(cb & 0xFFFFu), silu_bf(cb >> 16)));
                }
            }
            bar_sync(9, 384);
            if (sc) return;
            target = lds1(sb + M_EPOCH) + 1;
            const uint32_t tag = target & 0xFFFFu;
            if (warp == 11) {
                warp_arrive(BAR(B_WMFULL));
                mbar_wait(BAR(B_GEMV), 0);
                float sum = 0.f;
#pragma unroll
                for (int i = 0; i < 8; i++) sum += *(const float*)(smem + OFF_Y + HALF + 29696 + (i * 32 + (early ? lane & 15 : lane)) * 4);
                const uint32_t word = (pack2(sum, 0.f) << 16) | tag;
                if (gemv) {
                    uint32_t* mg = g_mod + mcol + (early ? (lane & 15) + (lane >> 4) * 4 * 6 * DM : lane);
#pragma unroll
                    for (int i = 0; i < 8; i++) if (i < 4 || !early) st_relaxed(mg + i * 6 * DM, word);
                }
                warp_arrive(BAR(B_WMFREE));
                PROFH(5);
            }
            const uint4* modp = (const uint4*)g_mod + (r & 7) * (6 * DM / 4);
            const bool p2 = warp == 11;
            mbar_wait(BAR(p2 ? B_PUB : B_XFULL + 4), 0);
#pragma unroll 1
            for (int it = p2 ? 0 : warp - 9; it < (p2 ? 2 : warp - 8); it++) {
                const int i0 = lane + 32 * it, imax = p2 ? 251 : 223;
                uint4 v[4];
#pragma unroll 1
                for (int n = 0;; n++) {
                    uint32_t bad = 0;
#pragma unroll
                    for (int k = 0; k < 4; k++) {
                        const int i = min(i0 + 64 * k, imax);
                        v[k] = ld_relaxed4(modp + (i < 224 ? (p2 ? 336 : 0) + i : (i < 238 ? 14 * j + i : 14 * j + i + 322)));
                        bad |= (v[k].x ^ tag) | (v[k].y ^ tag) | (v[k].z ^ tag) | (v[k].w ^ tag);
                    }
                    if (!(bad & 0xFFFFu)) break;
                    if (n > SPIN_LIMIT) __trap();
                }
#pragma unroll
                for (int k = 0; k < 4; k++) {
                    const int i = min(i0 + 64 * k, imax);
                    if (i < 224) {
                        const int isc = i >= 112, c4 = i - 112 * isc;
                        const float one = isc ? 1.f : 0.f;
                        const uint32_t a = sb + M_ST + (c4 >> 2) * 64 + (c4 & 1) * 32 + (c4 & 2) * 4 + (isc ? 0 : 4);
                        sts1(a, pack2(bf_hi(v[k].x) + one, bf_hi(v[k].y) + one));
                        sts1(a + 16, pack2(bf_hi(v[k].z) + one, bf_hi(v[k].w) + one));
                    } else {
                        sts4(sb + M_G + (i - 224) * 16, make_uint4(v[k].x & 0xFFFF0000u, v[k].y & 0xFFFF0000u, v[k].z & 0xFFFF0000u, v[k].w & 0xFFFF0000u));
                    }
                }
                warp_arrive(BAR(p2 ? B_MOD2 : B_MOD1));
            }
            if (warp == 9) PROFH(6);
            if (warp == 9) {
#pragma unroll 1
                for (int kv = 0; kv < 2; kv++) {
                    mbar_wait(BAR(B_PUB + kv), 0);
                    if (lane >= 1 && lane <= 2 && r >= lane) wait_flag(g_flag + kv * 128 + b - 8 * lane, target);
                    __syncwarp();
                    fence_async_global();
                    const uint32_t dst = sb + OFF_Y + (kv ? Y_VR : Y_K);
                    expect_e(BAR(B_KRFULL + kv), r >= 2 ? 28672 : r == 1 ? 14336 : 0);
                    if (r >= 2) bulk_e(dst, g_kv + (size_t)((b - 16) * 2 + kv) * 3584, 14336, BAR(B_KRFULL + kv));
                    if (r >= 1) bulk_e(dst + 14336, g_kv + (size_t)((b - 8) * 2 + kv) * 3584, 14336, BAR(B_KRFULL + kv));
                    PROFH(7 + kv);
                }
            } else if (warp == 11) {
                mbar_wait(BAR(B_VRFULL), 0);
                if (lane == 0) {
                    l2_prefetch((const char*)p.wg + (size_t)b * 12544, 12544);
                    l2_prefetch((const char*)p.wu + (size_t)b * 12544, 12544);
                    l2_prefetch((const char*)p.wd + (size_t)b * 12544, 12544);
                }
                __syncwarp();
            }
        }
        if (warp == 8 || warp == 11) {
            const int sec = warp == 11;
            int sl = 0;
#pragma unroll 1
            for (int s = 0; s < 28; s++) {
                const bool pa = s < 14;
                const uint32_t half = pa ? 8192 : 6144;
                mbar_wait(BAR(B_EMPTY + sl), (s >= 7 && s < 14) || s >= 21);
                expect_e(BAR(B_FULL + sl), half);
                tma3_e(sb + OFF_X + sl * 16384 + sec * half, &p.ga + (pa ? 0 : 2) + sec, 0, 32 * (pa ? s : s - 14), pa ? fa >> 6 : fb >> 5, BAR(B_FULL + sl));
                sl = sl == 6 ? 0 : sl + 1;
            }
            if (!sec) PROFH(3);
            sl = 0;
            int u = 0;
#pragma unroll 1
            for (int grp = 0; grp < 8; grp++) {
                const bool pa = grp < 4, own = grp == 3 || grp == 4;
                int sidx = pa ? grp : grp - 5;
                sidx = own ? nq : sidx + (sidx >= nq);
                const int ofs = 4 * kh + sidx;
                int f = 224 * ofs + ((ofs & 1) ? (pa ? 96 : 0) : (pa ? 0 : 128));
                if (sec && (grp == 0 || grp == 5)) { mbar_wait(BAR(B_HRDY + !pa), 0); fence_async_global(); }
#pragma unroll 1
                for (int k = pa ? 0 : 1; k < 4; k++, u++, f += 32) {
                    const uint32_t dst = sb + sl * 16384, bar = BAR(B_FULL + sl);
                    mbar_wait(BAR(B_EMPTY + sl), u >= 12 && u < 24);
                    if (!sec) {
                        expect_e(bar, 8192);
                        tma3_e(dst, &p.dn, 0, nq, f, bar);
                        tma3_e(dst + 4096, &p.dn, 64, nq, f, bar);
                    } else {
                        expect_e(bar, own ? 0 : 8192);
                        if (!own) bulk_e(dst + 8192, g_h2 + (size_t)r * (224 * 512) + f * 64, 8192, bar);
                    }
                    sl = sl == 11 ? 0 : sl + 1;
                }
            }
            if (!sec) PROFH(4);
            mbar_wait(BAR(B_DONE), 0);
        } else if (warp == 9) {
#pragma unroll 1
            for (int ev = 0; ev < 4; ev++) {
                mbar_wait(BAR(B_PUB + 2 + ev), 0);
                const uint32_t bar = BAR(B_GFULL + ev), dst = sb + (ev == 0 ? OFF_X : OFF_Y + (ev & 1) * HALF);
                const int tile = 2 * r + (ev & 1);
                const uint32_t* src = (ev < 2 ? g_o : g_x1) + (size_t)tile * 14336;
                expect_e(bar, ev < 2 ? HALF : HALF + 4096);
                uint32_t todo = 0xFF;
#pragma unroll 1
                for (int n = 0; todo; n++) {
                    uint32_t ok = __ballot_sync(~0u, (int)(ld_acquire(g_flag + (2 + ev) * 128 + 8 * r + (lane & 7)) - target) >= 0) & todo;
                    todo &= ~ok;
                    fence_async_global();
#pragma unroll 1
                    for (; ok; ok &= ok - 1) {
                        const int jj = __ffs(ok) - 1;
                        bulk_e(dst + jj * 7168, src + jj * 1792, 7168, bar);
                        if (ev >= 2) bulk_e(sb + OFF_X + X_STAT + (ev & 1) * 4096 + jj * 512, g_st + (tile * 8 + jj) * 64, 512, bar);
                    }
                    if (n > SPIN_LIMIT) __trap();
                }
            }
#pragma unroll 1
            for (int ps = 0; ps < 2; ps++) {
                mbar_wait(BAR(B_PUB + 6 + ps), 0);
                if (lane < 4) wait_flag(g_flag + (6 + ps) * 128 + 8 * r + 2 * lane + kh, target);
                warp_arrive(BAR(B_HRDY + ps));
                PROFH(10 + ps);
            }
        } else {
            if (lane == 0) {
#pragma unroll 1
                for (int k = 0; k < 8; k++) {
                    mbar_wait(BAR(B_PUB + k), 0);
                    fence_gpu();
                    st_relaxed(g_flag + k * 128 + b, target);
                    if (k == 5) PROFH1(9);
                }
            }
        }
    }
}

typedef CUresult (*EncodeFn)(CUtensorMap*, CUtensorMapDataType, cuuint32_t, void*, const cuuint64_t*, const cuuint64_t*, const cuuint32_t*,
                             const cuuint32_t*, CUtensorMapInterleave, CUtensorMapSwizzle, CUtensorMapL2promotion, CUtensorMapFloatOOBfill);

static void make_map(EncodeFn fn, CUtensorMap* m, const void* ptr, uint64_t d0, uint64_t d1, uint64_t d2, uint64_t s1, uint64_t s2,
                     uint32_t b0, uint32_t b1, uint32_t b2, CUtensorMapSwizzle sw) {
    cuuint64_t dims[3] = {d0, d1, d2}, strides[2] = {s1, s2};
    cuuint32_t box[3] = {b0, b1, b2}, es[3] = {1, 1, 1};
    CUresult rc = fn(m, CU_TENSOR_MAP_DATA_TYPE_BFLOAT16, 3, (void*)ptr, dims, strides, box, es, CU_TENSOR_MAP_INTERLEAVE_NONE, sw,
                     CU_TENSOR_MAP_L2_PROMOTION_L2_128B, CU_TENSOR_MAP_FLOAT_OOB_FILL_NONE);
    (void)rc;
}

extern "C" void kernel_launch(void* const* d_in, const int* in_sizes, int n_in, void* d_out, int out_size) {
    (void)in_sizes; (void)n_in; (void)out_size;
    static EncodeFn fn = nullptr;
    if (!fn) {
        cudaDriverEntryPointQueryResult st;
        cudaGetDriverEntryPoint("cuTensorMapEncodeTiled", (void**)&fn, cudaEnableDefault, &st);
        cudaFuncSetAttribute(fused_block_kernel, cudaFuncAttributeMaxDynamicSharedMemorySize, SMEM_BYTES);
    }
    Params p;
    p.x = (const bf16*)d_in[0];
    const bf16* wqkv = (const bf16*)d_in[1];
    p.wqkv = wqkv;
    p.wop = (const bf16*)d_in[2];
    p.wg = (const bf16*)d_in[4];
    p.wu = (const bf16*)d_in[5];
    p.wd = (const bf16*)d_in[6];
    p.c = (const bf16*)d_in[7];
    p.wmod = (const bf16*)d_in[8];
    p.out = (bf16*)d_out;
    p.zero = 0;
    make_map(fn, &p.wm, p.wmod, 2688, 448, 1, 5376, 5376 * 448, 16, 224, 1, CU_TENSOR_MAP_SWIZZLE_NONE);
    make_map(fn, &p.xm, p.x, 448, 2048, 1, 896, 896 * 2048, 64, 128, 1, CU_TENSOR_MAP_SWIZZLE_128B);
    make_map(fn, &p.qkv, wqkv, 1344, 448, 1, 2688, 2688 * 448, 64, 224, 1, CU_TENSOR_MAP_SWIZZLE_128B);
    make_map(fn, &p.wo, p.wop, 448, 448, 1, 896, 896 * 448, 64, 224, 1, CU_TENSOR_MAP_SWIZZLE_128B);
    make_map(fn, &p.ga, p.wg, 64, 448, 28, 3584, 128, 64, 32, 2, CU_TENSOR_MAP_SWIZZLE_128B);
    make_map(fn, &p.ua, p.wu, 64, 448, 28, 3584, 128, 64, 32, 2, CU_TENSOR_MAP_SWIZZLE_128B);
    make_map(fn, &p.gb, p.wg, 32, 448, 56, 3584, 64, 32, 32, 3, CU_TENSOR_MAP_SWIZZLE_64B);
    make_map(fn, &p.ub, p.wu, 32, 448, 56, 3584, 64, 32, 32, 3, CU_TENSOR_MAP_SWIZZLE_64B);
    make_map(fn, &p.dn, p.wd, 112, 4, 1792, 224, 896, 64, 1, 32, CU_TENSOR_MAP_SWIZZLE_128B);
    fused_block_kernel<<<GRID, 384, SMEM_BYTES>>>(p);
}
```

```cpp
#include <cuda_runtime.h>
#include <cuda_bf16.h>
#include <cuda.h>
#include <stdint.h>

typedef __nv_bfloat16 bf16;

template<int TB> __device__ __forceinline__ void wgmma_rs_56(float* d, uint32_t a0, uint32_t a1, uint32_t a2, uint32_t a3, uint64_t db, int sd) {
  asm volatile("{\n.reg .pred p;\nsetp.ne.b32 p, %33, 0;\n"
    "wgmma.mma_async.sync.aligned.m64n56k16.f32.bf16.bf16 {%0,%1,%2,%3,%4,%5,%6,%7,%8,%9,%10,%11,%12,%13,%14,%15,%16,%17,%18,%19,%20,%21,%22,%23,%24,%25,%26,%27}, {%28,%29,%30,%31}, %32, p, 1, 1, %34;\n}\n"
    : "+f"(d[0]),"+f"(d[1]),"+f"(d[2]),"+f"(d[3]),"+f"(d[4]),"+f"(d[5]),"+f"(d[6]),"+f"(d[7]),"+f"(d[8]),"+f"(d[9]),"+f"(d[10]),"+f"(d[11]),"+f"(d[12]),"+f"(d[13]),"+f"(d[14]),"+f"(d[15]),"+f"(d[16]),"+f"(d[17]),"+f"(d[18]),"+f"(d[19]),"+f"(d[20]),"+f"(d[21]),"+f"(d[22]),"+f"(d[23]),"+f"(d[24]),"+f"(d[25]),"+f"(d[26]),"+f"(d[27])
    : "r"(a0), "r"(a1), "r"(a2), "r"(a3), "l"(db), "r"(sd), "n"(TB));
}
template<int TB> __device__ __forceinline__ void wgmma_ss_56(float* d, uint64_t da, uint64_t db, int sd) {
  asm volatile("{\n.reg .pred p;\nsetp.ne.b32 p, %30, 0;\n"
    "wgmma.mma_async.sync.aligned.m64n56k16.f32.bf16.bf16 {%0,%1,%2,%3,%4,%5,%6,%7,%8,%9,%10,%11,%12,%13,%14,%15,%16,%17,%18,%19,%20,%21,%22,%23,%24,%25,%26,%27}, %28, %29, p, 1, 1, 0, %31;\n}\n"
    : "+f"(d[0]),"+f"(d[1]),"+f"(d[2]),"+f"(d[3]),"+f"(d[4]),"+f"(d[5]),"+f"(d[6]),"+f"(d[7]),"+f"(d[8]),"+f"(d[9]),"+f"(d[10]),"+f"(d[11]),"+f"(d[12]),"+f"(d[13]),"+f"(d[14]),"+f"(d[15]),"+f"(d[16]),"+f"(d[17]),"+f"(d[18]),"+f"(d[19]),"+f"(d[20]),"+f"(d[21]),"+f"(d[22]),"+f"(d[23]),"+f"(d[24]),"+f"(d[25]),"+f"(d[26]),"+f"(d[27])
    : "l"(da), "l"(db), "r"(sd), "n"(TB));
}
template<int TB> __device__ __forceinline__ void wgmma_rs_256(float* d, uint32_t a0, uint32_t a1, uint32_t a2, uint32_t a3, uint64_t db, int sd) {
  asm volatile("{\n.reg .pred p;\nsetp.ne.b32 p, %133, 0;\n"
    "wgmma.mma_async.sync.aligned.m64n256k16.f32.bf16.bf16 {%0,%1,%2,%3,%4,%5,%6,%7,%8,%9,%10,%11,%12,%13,%14,%15,%16,%17,%18,%19,%20,%21,%22,%23,%24,%25,%26,%27,%28,%29,%30,%31,%32,%33,%34,%35,%36,%37,%38,%39,%40,%41,%42,%43,%44,%45,%46,%47,%48,%49,%50,%51,%52,%53,%54,%55,%56,%57,%58,%59,%60,%61,%62,%63,%64,%65,%66,%67,%68,%69,%70,%71,%72,%73,%74,%75,%76,%77,%78,%79,%80,%81,%82,%83,%84,%85,%86,%87,%88,%89,%90,%91,%92,%93,%94,%95,%96,%97,%98,%99,%100,%101,%102,%103,%104,%105,%106,%107,%108,%109,%110,%111,%112,%113,%114,%115,%116,%117,%118,%119,%120,%121,%122,%123,%124,%125,%126,%127}, {%128,%129,%130,%131}, %132, p, 1, 1, %134;\n}\n"
    : "+f"(d[0]),"+f"(d[1]),"+f"(d[2]),"+f"(d[3]),"+f"(d[4]),"+f"(d[5]),"+f"(d[6]),"+f"(d[7]),"+f"(d[8]),"+f"(d[9]),"+f"(d[10]),"+f"(d[11]),"+f"(d[12]),"+f"(d[13]),"+f"(d[14]),"+f"(d[15]),"+f"(d[16]),"+f"(d[17]),"+f"(d[18]),"+f"(d[19]),"+f"(d[20]),"+f"(d[21]),"+f"(d[22]),"+f"(d[23]),"+f"(d[24]),"+f"(d[25]),"+f"(d[26]),"+f"(d[27]),"+f"(d[28]),"+f"(d[29]),"+f"(d[30]),"+f"(d[31]),"+f"(d[32]),"+f"(d[33]),"+f"(d[34]),"+f"(d[35]),"+f"(d[36]),"+f"(d[37]),"+f"(d[38]),"+f"(d[39]),"+f"(d[40]),"+f"(d[41]),"+f"(d[42]),"+f"(d[43]),"+f"(d[44]),"+f"(d[45]),"+f"(d[46]),"+f"(d[47]),"+f"(d[48]),"+f"(d[49]),"+f"(d[50]),"+f"(d[51]),"+f"(d[52]),"+f"(d[53]),"+f"(d[54]),"+f"(d[55]),"+f"(d[56]),"+f"(d[57]),"+f"(d[58]),"+f"(d[59]),"+f"(d[60]),"+f"(d[61]),"+f"(d[62]),"+f"(d[63]),"+f"(d[64]),"+f"(d[65]),"+f"(d[66]),"+f"(d[67]),"+f"(d[68]),"+f"(d[69]),"+f"(d[70]),"+f"(d[71]),"+f"(d[72]),"+f"(d[73]),"+f"(d[74]),"+f"(d[75]),"+f"(d[76]),"+f"(d[77]),"+f"(d[78]),"+f"(d[79]),"+f"(d[80]),"+f"(d[81]),"+f"(d[82]),"+f"(d[83]),"+f"(d[84]),"+f"(d[85]),"+f"(d[86]),"+f"(d[87]),"+f"(d[88]),"+f"(d[89]),"+f"(d[90]),"+f"(d[91]),"+f"(d[92]),"+f"(d[93]),"+f"(d[94]),"+f"(d[95]),"+f"(d[96]),"+f"(d[97]),"+f"(d[98]),"+f"(d[99]),"+f"(d[100]),"+f"(d[101]),"+f"(d[102]),"+f"(d[103]),"+f"(d[104]),"+f"(d[105]),"+f"(d[106]),"+f"(d[107]),"+f"(d[108]),"+f"(d[109]),"+f"(d[110]),"+f"(d[111]),"+f"(d[112]),"+f"(d[113]),"+f"(d[114]),"+f"(d[115]),"+f"(d[116]),"+f"(d[117]),"+f"(d[118]),"+f"(d[119]),"+f"(d[120]),"+f"(d[121]),"+f"(d[122]),"+f"(d[123]),"+f"(d[124]),"+f"(d[125]),"+f"(d[126]),"+f"(d[127])
    : "r"(a0), "r"(a1), "r"(a2), "r"(a3), "l"(db), "r"(sd), "n"(TB));
}
template<int TB> __device__ __forceinline__ void wgmma_ss_192(float* d, uint64_t da, uint64_t db, int sd) {
  asm volatile("{\n.reg .pred p;\nsetp.ne.b32 p, %98, 0;\n"
    "wgmma.mma_async.sync.aligned.m64n192k16.f32.bf16.bf16 {%0,%1,%2,%3,%4,%5,%6,%7,%8,%9,%10,%11,%12,%13,%14,%15,%16,%17,%18,%19,%20,%21,%22,%23,%24,%25,%26,%27,%28,%29,%30,%31,%32,%33,%34,%35,%36,%37,%38,%39,%40,%41,%42,%43,%44,%45,%46,%47,%48,%49,%50,%51,%52,%53,%54,%55,%56,%57,%58,%59,%60,%61,%62,%63,%64,%65,%66,%67,%68,%69,%70,%71,%72,%73,%74,%75,%76,%77,%78,%79,%80,%81,%82,%83,%84,%85,%86,%87,%88,%89,%90,%91,%92,%93,%94,%95}, %96, %97, p, 1, 1, 0, %99;\n}\n"
    : "+f"(d[0]),"+f"(d[1]),"+f"(d[2]),"+f"(d[3]),"+f"(d[4]),"+f"(d[5]),"+f"(d[6]),"+f"(d[7]),"+f"(d[8]),"+f"(d[9]),"+f"(d[10]),"+f"(d[11]),"+f"(d[12]),"+f"(d[13]),"+f"(d[14]),"+f"(d[15]),"+f"(d[16]),"+f"(d[17]),"+f"(d[18]),"+f"(d[19]),"+f"(d[20]),"+f"(d[21]),"+f"(d[22]),"+f"(d[23]),"+f"(d[24]),"+f"(d[25]),"+f"(d[26]),"+f"(d[27]),"+f"(d[28]),"+f"(d[29]),"+f"(d[30]),"+f"(d[31]),"+f"(d[32]),"+f"(d[33]),"+f"(d[34]),"+f"(d[35]),"+f"(d[36]),"+f"(d[37]),"+f"(d[38]),"+f"(d[39]),"+f"(d[40]),"+f"(d[41]),"+f"(d[42]),"+f"(d[43]),"+f"(d[44]),"+f"(d[45]),"+f"(d[46]),"+f"(d[47]),"+f"(d[48]),"+f"(d[49]),"+f"(d[50]),"+f"(d[51]),"+f"(d[52]),"+f"(d[53]),"+f"(d[54]),"+f"(d[55]),"+f"(d[56]),"+f"(d[57]),"+f"(d[58]),"+f"(d[59]),"+f"(d[60]),"+f"(d[61]),"+f"(d[62]),"+f"(d[63]),"+f"(d[64]),"+f"(d[65]),"+f"(d[66]),"+f"(d[67]),"+f"(d[68]),"+f"(d[69]),"+f"(d[70]),"+f"(d[71]),"+f"(d[72]),"+f"(d[73]),"+f"(d[74]),"+f"(d[75]),"+f"(d[76]),"+f"(d[77]),"+f"(d[78]),"+f"(d[79]),"+f"(d[80]),"+f"(d[81]),"+f"(d[82]),"+f"(d[83]),"+f"(d[84]),"+f"(d[85]),"+f"(d[86]),"+f"(d[87]),"+f"(d[88]),"+f"(d[89]),"+f"(d[90]),"+f"(d[91]),"+f"(d[92]),"+f"(d[93]),"+f"(d[94]),"+f"(d[95])
    : "l"(da), "l"(db), "r"(sd), "n"(TB));
}
template<int TB> __device__ __forceinline__ void wgmma_ss_112(float* d, uint64_t da, uint64_t db, int sd) {
  asm volatile("{\n.reg .pred p;\nsetp.ne.b32 p, %58, 0;\n"
    "wgmma.mma_async.sync.aligned.m64n112k16.f32.bf16.bf16 {%0,%1,%2,%3,%4,%5,%6,%7,%8,%9,%10,%11,%12,%13,%14,%15,%16,%17,%18,%19,%20,%21,%22,%23,%24,%25,%26,%27,%28,%29,%30,%31,%32,%33,%34,%35,%36,%37,%38,%39,%40,%41,%42,%43,%44,%45,%46,%47,%48,%49,%50,%51,%52,%53,%54,%55}, %56, %57, p, 1, 1, 0, %59;\n}\n"
    : "+f"(d[0]),"+f"(d[1]),"+f"(d[2]),"+f"(d[3]),"+f"(d[4]),"+f"(d[5]),"+f"(d[6]),"+f"(d[7]),"+f"(d[8]),"+f"(d[9]),"+f"(d[10]),"+f"(d[11]),"+f"(d[12]),"+f"(d[13]),"+f"(d[14]),"+f"(d[15]),"+f"(d[16]),"+f"(d[17]),"+f"(d[18]),"+f"(d[19]),"+f"(d[20]),"+f"(d[21]),"+f"(d[22]),"+f"(d[23]),"+f"(d[24]),"+f"(d[25]),"+f"(d[26]),"+f"(d[27]),"+f"(d[28]),"+f"(d[29]),"+f"(d[30]),"+f"(d[31]),"+f"(d[32]),"+f"(d[33]),"+f"(d[34]),"+f"(d[35]),"+f"(d[36]),"+f"(d[37]),"+f"(d[38]),"+f"(d[39]),"+f"(d[40]),"+f"(d[41]),"+f"(d[42]),"+f"(d[43]),"+f"(d[44]),"+f"(d[45]),"+f"(d[46]),"+f"(d[47]),"+f"(d[48]),"+f"(d[49]),"+f"(d[50]),"+f"(d[51]),"+f"(d[52]),"+f"(d[53]),"+f"(d[54]),"+f"(d[55])
    : "l"(da), "l"(db), "r"(sd), "n"(TB));
}
template<int TB> __device__ __forceinline__ void wgmma_rs_112(float* d, uint32_t a0, uint32_t a1, uint32_t a2, uint32_t a3, uint64_t db, int sd) {
  asm volatile("{\n.reg .pred p;\nsetp.ne.b32 p, %61, 0;\n"
    "wgmma.mma_async.sync.aligned.m64n112k16.f32.bf16.bf16 {%0,%1,%2,%3,%4,%5,%6,%7,%8,%9,%10,%11,%12,%13,%14,%15,%16,%17,%18,%19,%20,%21,%22,%23,%24,%25,%26,%27,%28,%29,%30,%31,%32,%33,%34,%35,%36,%37,%38,%39,%40,%41,%42,%43,%44,%45,%46,%47,%48,%49,%50,%51,%52,%53,%54,%55}, {%56,%57,%58,%59}, %60, p, 1, 1, %62;\n}\n"
    : "+f"(d[0]),"+f"(d[1]),"+f"(d[2]),"+f"(d[3]),"+f"(d[4]),"+f"(d[5]),"+f"(d[6]),"+f"(d[7]),"+f"(d[8]),"+f"(d[9]),"+f"(d[10]),"+f"(d[11]),"+f"(d[12]),"+f"(d[13]),"+f"(d[14]),"+f"(d[15]),"+f"(d[16]),"+f"(d[17]),"+f"(d[18]),"+f"(d[19]),"+f"(d[20]),"+f"(d[21]),"+f"(d[22]),"+f"(d[23]),"+f"(d[24]),"+f"(d[25]),"+f"(d[26]),"+f"(d[27]),"+f"(d[28]),"+f"(d[29]),"+f"(d[30]),"+f"(d[31]),"+f"(d[32]),"+f"(d[33]),"+f"(d[34]),"+f"(d[35]),"+f"(d[36]),"+f"(d[37]),"+f"(d[38]),"+f"(d[39]),"+f"(d[40]),"+f"(d[41]),"+f"(d[42]),"+f"(d[43]),"+f"(d[44]),"+f"(d[45]),"+f"(d[46]),"+f"(d[47]),"+f"(d[48]),"+f"(d[49]),"+f"(d[50]),"+f"(d[51]),"+f"(d[52]),"+f"(d[53]),"+f"(d[54]),"+f"(d[55])
    : "r"(a0), "r"(a1), "r"(a2), "r"(a3), "l"(db), "r"(sd), "n"(TB));
}

constexpr int DM = 448;
constexpr int NCTA = 128;
#define MAPPING 1
#define GRID 132
#define PINGPONG 0
#define MAP_S 4
constexpr int SPIN_LIMIT = 1 << 22;

constexpr uint32_t OFF_X = 0, OFF_Y = 114688, OFF_MISC = 229376, SMEM_BYTES = 232448;
constexpr uint32_t Y_VR = 0, Y_K = 28672, Y_KOWN = 57344, Y_VOWN = 71680, Y_Q = 86016;
constexpr uint32_t HALF = 57344;
constexpr uint32_t M_BAR = OFF_MISC;
constexpr uint32_t M_ST = OFF_MISC + 512;
constexpr uint32_t M_G = OFF_MISC + 2304;
constexpr uint32_t M_EPOCH = OFF_MISC + 3040;
enum { B_XFULL = 0, B_FULLK = 7, B_FULLV = 8, B_FULLQ, B_KRFULL, B_VRFULL, B_WOFULL, B_XCH, B_FULL = 16, B_MOD1 = 28, B_MOD2, B_WMFULL,
       B_EMPTY = 32, B_XFREE = B_EMPTY + 12, B_GEMV, B_PEER, B_DONE,
       B_PUB = 48,
       B_WMFREE = 56, B_HRDY, B_GFULL = B_HRDY + 2 };
constexpr uint32_t X_STAT = 49152;

__device__ uint32_t g_ticket;
__device__ __align__(128) uint32_t g_mod[8 * 6 * DM];
__device__ __align__(128) uint32_t g_flag[8 * 16 * 8];
__device__ __align__(128) uint32_t g_kv[17 * 8 * 2 * 3584];
__device__ __align__(128) uint32_t g_o[34 * 14336];
__device__ __align__(128) uint32_t g_x1[34 * 14336];
__device__ __align__(128) float2 g_st[34 * 8 * 64];
__device__ __align__(128) uint32_t g_h2[17 * 224 * 512];
#define PROFH(id)
#define PROFH1(id)
#define PROFC(id)

struct alignas(64) Params {
    CUtensorMap wm, xm, qkv, wo, ga, ua, gb, ub, dn;
    const bf16 *x, *c, *wqkv, *wmod, *wg, *wu, *wd, *wop;
    bf16* out;
    uint32_t zero;
};

__device__ __forceinline__ void mbar_init(uint32_t bar, int cnt) { asm volatile("mbarrier.init.shared::cta.b64 [%0], %1;" ::"r"(bar), "r"(cnt) : "memory"); }
__device__ __forceinline__ void mbar_expect_tx(uint32_t bar, uint32_t bytes) { asm volatile("mbarrier.arrive.expect_tx.shared::cta.b64 _, [%0], %1;" ::"r"(bar), "r"(bytes) : "memory"); }
__device__ __forceinline__ void mbar_arrive(uint32_t bar) { asm volatile("mbarrier.arrive.shared::cta.b64 _, [%0];" ::"r"(bar) : "memory"); }
__device__ __forceinline__ void mbar_wait(uint32_t bar, uint32_t parity) {
    uint32_t ok; int n = 0;
    do {
        asm volatile("{\n.reg .pred p;\nmbarrier.try_wait.parity.shared::cta.b64 p, [%1], %2;\nselp.u32 %0, 1, 0, p;\n}" : "=r"(ok) : "r"(bar), "r"(parity) : "memory");
        if (++n > SPIN_LIMIT) __trap();
    } while (!ok);
}
__device__ __forceinline__ void mbar_wait_cluster(uint32_t bar, uint32_t parity) {
    uint32_t ok; int n = 0;
    do {
        asm volatile("{\n.reg .pred p;\nmbarrier.try_wait.parity.acquire.cluster.shared::cta.b64 p, [%1], %2;\nselp.u32 %0, 1, 0, p;\n}" : "=r"(ok) : "r"(bar), "r"(parity) : "memory");
        if (++n > SPIN_LIMIT) __trap();
    } while (!ok);
}
__device__ __forceinline__ void warp_arrive(uint32_t bar) {
    __syncwarp();
    asm volatile("{\n.reg .pred p;\nelect.sync _|p, 0xffffffff;\n@p mbarrier.arrive.shared::cta.b64 _, [%0];\n}" ::"r"(bar) : "memory");
}
__device__ __forceinline__ int opaque(int v) { return __shfl_sync(~0u, v, 0); }
__device__ __forceinline__ int fresh_tid() { int v; asm volatile("mov.u32 %0, %%tid.x;" : "=r"(v)); return v; }
__device__ __forceinline__ void bar_sync(int id, int n) { asm volatile("bar.sync %0, %1;" ::"r"(id), "r"(n) : "memory"); }
__device__ __forceinline__ void bar_arrive(int id, int n) { asm volatile("bar.arrive %0, %1;" ::"r"(id), "r"(n) : "memory"); }
__device__ __forceinline__ void fence_async_smem() { asm volatile("fence.proxy.async.shared::cta;" ::: "memory"); }
__device__ __forceinline__ void fence_async_global() { asm volatile("fence.proxy.async.global;" ::: "memory"); }
__device__ __forceinline__ void fence_gpu() { asm volatile("fence.acq_rel.gpu;" ::: "memory"); }
__device__ __forceinline__ void tma3(uint32_t dst, const CUtensorMap* m, int c0, int c1, int c2, uint32_t bar) {
    asm volatile("cp.async.bulk.tensor.3d.shared::cluster.global.mbarrier::complete_tx::bytes [%0], [%1, {%3, %4, %5}], [%2];"
                 ::"r"(dst), "l"(m), "r"(bar), "r"(c0), "r"(c1), "r"(c2) : "memory");
}
__device__ __forceinline__ void bulk_load(uint32_t dst, const void* src, uint32_t bytes, uint32_t bar) {
    asm volatile("cp.async.bulk.shared::cluster.global.mbarrier::complete_tx::bytes [%0], [%1], %2, [%3];" ::"r"(dst), "l"(src), "r"(bytes), "r"(bar) : "memory");
}
__device__ __forceinline__ void expect_e(uint32_t bar, uint32_t bytes) {
    asm volatile("{\n.reg .pred p;\nelect.sync _|p, 0xffffffff;\n@p mbarrier.arrive.expect_tx.shared::cta.b64 _, [%0], %1;\n}" ::"r"(bar), "r"(bytes) : "memory");
}
__device__ __forceinline__ void tma3_e(uint32_t dst, const CUtensorMap* m, int c0, int c1, int c2, uint32_t bar) {
    asm volatile("{\n.reg .pred p;\nelect.sync _|p, 0xffffffff;\n@p cp.async.bulk.tensor.3d.shared::cluster.global.mbarrier::complete_tx::bytes [%0], [%1, {%3, %4, %5}], [%2];\n}"
                 ::"r"(dst), "l"(m), "r"(bar), "r"(c0), "r"(c1), "r"(c2) : "memory");
}
__device__ __forceinline__ void bulk_e(uint32_t dst, const void* src, uint32_t bytes, uint32_t bar) {
    asm volatile("{\n.reg .pred p;\nelect.sync _|p, 0xffffffff;\n@p cp.async.bulk.shared::cluster.global.mbarrier::complete_tx::bytes [%0], [%1], %2, [%3];\n}"
                 ::"r"(dst), "l"(src), "r"(bytes), "r"(bar) : "memory");
}
__device__ __forceinline__ void init_e(uint32_t bar, int cnt) {
    asm volatile("{\n.reg .pred p;\nelect.sync _|p, 0xffffffff;\n@p mbarrier.init.shared::cta.b64 [%0], %1;\n}" ::"r"(bar), "r"(cnt) : "memory");
}
__device__ __forceinline__ void l2_prefetch(const void* src, uint32_t bytes) { asm volatile("cp.async.bulk.prefetch.L2.global [%0], %1;" ::"l"(src), "r"(bytes) : "memory"); }
__device__ __forceinline__ uint32_t ld_relaxed(const uint32_t* p) { uint32_t v; asm volatile("ld.relaxed.gpu.global.u32 %0, [%1];" : "=r"(v) : "l"(p) : "memory"); return v; }
__device__ __forceinline__ void st_relaxed(uint32_t* p, uint32_t v) { asm volatile("st.relaxed.gpu.global.u32 [%0], %1;" ::"l"(p), "r"(v) : "memory"); }
__device__ __forceinline__ uint4 ld_relaxed4(const uint4* p) { uint4 v; asm volatile("ld.relaxed.gpu.global.v4.u32 {%0,%1,%2,%3}, [%4];" : "=r"(v.x), "=r"(v.y), "=r"(v.z), "=r"(v.w) : "l"(p) : "memory"); return v; }
__device__ __forceinline__ void st_relaxed4(uint4* p, uint4 v) { asm volatile("st.relaxed.gpu.global.v4.u32 [%0], {%1,%2,%3,%4};" ::"l"(p), "r"(v.x), "r"(v.y), "r"(v.z), "r"(v.w) : "memory"); }
__device__ __forceinline__ uint4 ldg_nc4(const void* p) { uint4 v; asm volatile("ld.global.nc.L1::no_allocate.v4.u32 {%0,%1,%2,%3}, [%4];" : "=r"(v.x), "=r"(v.y), "=r"(v.z), "=r"(v.w) : "l"(p)); return v; }
__device__ __forceinline__ uint32_t ldg_nc(const void* p) { uint32_t v; asm volatile("ld.global.nc.u32 %0, [%1];" : "=r"(v) : "l"(p)); return v; }
__device__ __forceinline__ uint32_t ld_acquire(const uint32_t* p) { uint32_t v; asm volatile("ld.acquire.gpu.global.u32 %0, [%1];" : "=r"(v) : "l"(p) : "memory"); return v; }
__device__ __forceinline__ uint4 lds4(uint32_t a) { uint4 v; asm volatile("ld.shared.v4.u32 {%0,%1,%2,%3}, [%4];" : "=r"(v.x), "=r"(v.y), "=r"(v.z), "=r"(v.w) : "r"(a) : "memory"); return v; }
__device__ __forceinline__ float2 lds2f(uint32_t a) { float2 v; asm volatile("ld.shared.v2.f32 {%0,%1}, [%2];" : "=f"(v.x), "=f"(v.y) : "r"(a) : "memory"); return v; }
__device__ __forceinline__ uint32_t lds1(uint32_t a) { uint32_t v; asm volatile("ld.shared.u32 %0, [%1];" : "=r"(v) : "r"(a) : "memory"); return v; }
__device__ __forceinline__ void sts4(uint32_t a, uint4 v) { asm volatile("st.shared.v4.u32 [%0], {%1,%2,%3,%4};" ::"r"(a), "r"(v.x), "r"(v.y), "r"(v.z), "r"(v.w) : "memory"); }
__device__ __forceinline__ void sts2(uint32_t a, uint32_t x, uint32_t y) { asm volatile("st.shared.v2.u32 [%0], {%1,%2};" ::"r"(a), "r"(x), "r"(y) : "memory"); }
__device__ __forceinline__ void sts1(uint32_t a, uint32_t v) { asm volatile("st.shared.u32 [%0], %1;" ::"r"(a), "r"(v) : "memory"); }
__device__ __forceinline__ void stsm4(uint32_t a, uint32_t r0, uint32_t r1, uint32_t r2, uint32_t r3) {
    asm volatile("stmatrix.sync.aligned.m8n8.x4.shared.b16 [%0], {%1,%2,%3,%4};" ::"r"(a), "r"(r0), "r"(r1), "r"(r2), "r"(r3));
}
__device__ __forceinline__ uint32_t pack2(float lo, float hi) { uint32_t r; asm("cvt.rn.bf16x2.f32 %0, %1, %2;" : "=r"(r) : "f"(hi), "f"(lo)); return r; }
__device__ __forceinline__ uint32_t pack2_relu(float lo, float hi) { uint32_t r; asm("cvt.rn.relu.bf16x2.f32 %0, %1, %2;" : "=r"(r) : "f"(hi), "f"(lo)); return r; }
__device__ __forceinline__ uint32_t hfma2(uint32_t a, uint32_t b, uint32_t c) { uint32_t r; asm("fma.rn.bf16x2 %0, %1, %2, %3;" : "=r"(r) : "r"(a), "r"(b), "r"(c)); return r; }
__device__ __forceinline__ uint32_t hmul2(uint32_t a, uint32_t b) { uint32_t r; asm("mul.rn.bf16x2 %0, %1, %2;" : "=r"(r) : "r"(a), "r"(b)); return r; }
__device__ __forceinline__ float bf_lo(uint32_t v) { return __uint_as_float(v << 16); }
__device__ __forceinline__ float bf_hi(uint32_t v) { return __uint_as_float(v & 0xFFFF0000u); }
__device__ __forceinline__ float bf_round(float v) { return bf_lo(pack2(v, 0.f)); }
__device__ __forceinline__ float ex2(float x) { float r; asm("ex2.approx.ftz.f32 %0, %1;" : "=f"(r) : "f"(x)); return r; }
__device__ __forceinline__ void mma16816(float* d, uint32_t a0, uint32_t a1, uint32_t a2, uint32_t a3, uint32_t b0, uint32_t b1) {
    asm("mma.sync.aligned.m16n8k16.row.col.f32.bf16.bf16.f32 {%0,%1,%2,%3}, {%4,%5,%6,%7}, {%8,%9}, {%0,%1,%2,%3};"
        : "+f"(d[0]), "+f"(d[1]), "+f"(d[2]), "+f"(d[3]) : "r"(a0), "r"(a1), "r"(a2), "r"(a3), "r"(b0), "r"(b1));
}
__device__ __forceinline__ void mma16816_first(float* d, uint32_t a0, uint32_t a1, uint32_t a2, uint32_t a3, uint32_t b0, uint32_t b1) {
    asm volatile("mma.sync.aligned.m16n8k16.row.col.f32.bf16.bf16.f32 {%0,%1,%2,%3}, {%4,%5,%6,%7}, {%8,%9}, {%10,%10,%10,%10};"
        : "=f"(d[0]), "=f"(d[1]), "=f"(d[2]), "=f"(d[3]) : "r"(a0), "r"(a1), "r"(a2), "r"(a3), "r"(b0), "r"(b1), "f"(0.f));
}
__device__ __forceinline__ void mma16816_v(float* d, uint32_t a0, uint32_t a1, uint32_t a2, uint32_t a3, uint32_t b0, uint32_t b1) {
    asm volatile("mma.sync.aligned.m16n8k16.row.col.f32.bf16.bf16.f32 {%0,%1,%2,%3}, {%4,%5,%6,%7}, {%8,%9}, {%0,%1,%2,%3};"
        : "+f"(d[0]), "+f"(d[1]), "+f"(d[2]), "+f"(d[3]) : "r"(a0), "r"(a1), "r"(a2), "r"(a3), "r"(b0), "r"(b1));
}
__device__ __forceinline__ void mma1688(float* d, uint32_t a0, uint32_t a1, uint32_t b0) {
    asm("mma.sync.aligned.m16n8k8.row.col.f32.bf16.bf16.f32 {%0,%1,%2,%3}, {%4,%5}, {%6}, {%0,%1,%2,%3};"
        : "+f"(d[0]), "+f"(d[1]), "+f"(d[2]), "+f"(d[3]) : "r"(a0), "r"(a1), "r"(b0));
}
__device__ __forceinline__ void ldsm4(uint32_t a, uint32_t* r) {
    asm volatile("ldmatrix.sync.aligned.m8n8.x4.shared.b16 {%0,%1,%2,%3}, [%4];" : "=r"(r[0]), "=r"(r[1]), "=r"(r[2]), "=r"(r[3]) : "r"(a));
}
__device__ __forceinline__ void ldsm4t(uint32_t a, uint32_t* r) {
    asm volatile("ldmatrix.sync.aligned.m8n8.x4.trans.shared.b16 {%0,%1,%2,%3}, [%4];" : "=r"(r[0]), "=r"(r[1]), "=r"(r[2]), "=r"(r[3]) : "r"(a));
}
__device__ __forceinline__ float rcp(float x) { float r; asm("rcp.approx.ftz.f32 %0, %1;" : "=f"(r) : "f"(x)); return r; }
__device__ __forceinline__ uint2 ld_relaxed2(const void* p) { uint2 v; asm volatile("ld.relaxed.gpu.global.v2.u32 {%0,%1}, [%2];" : "=r"(v.x), "=r"(v.y) : "l"(p) : "memory"); return v; }
__device__ __forceinline__ void st_relaxed2(void* p, uint32_t x, uint32_t y) { asm volatile("st.relaxed.gpu.global.v2.u32 [%0], {%1,%2};" ::"l"(p), "r"(max(x, 1u)), "r"(max(y, 1u)) : "memory"); }
__device__ __forceinline__ constexpr uint64_t dconst(uint32_t lbo, uint32_t sbo, uint32_t swz) {
    return ((uint64_t)(lbo >> 4) << 16) | ((uint64_t)(sbo >> 4) << 32) | ((uint64_t)swz << 62);
}
__device__ __forceinline__ uint64_t mkdesc(uint32_t addr, uint64_t c) { return c | (uint64_t)((addr & 0x3FFFF) >> 4); }
#define WG_FENCE() asm volatile("wgmma.fence.sync.aligned;" ::: "memory")
#define WG_COMMIT() asm volatile("wgmma.commit_group.sync.aligned;" ::: "memory")
#define WG_WAIT(n) asm volatile("wgmma.wait_group.sync.aligned %0;" ::"n"(n) : "memory")
template <int N> __device__ __forceinline__ void reg_fence(float* d) {
#pragma unroll
    for (int i = 0; i < N; i++) asm volatile("" : "+f"(d[i])::"memory");
}
template <int N> __device__ __forceinline__ void reg_def(float* d) {
#pragma unroll
    for (int i = 0; i < N; i++) asm volatile("" : "=f"(d[i]));
}
template <int N> __device__ __forceinline__ void reg_def(uint32_t* d) {
#pragma unroll
    for (int i = 0; i < N; i++) asm volatile("" : "=r"(d[i]));
}
__device__ __forceinline__ bool is_unset(uint4 v) { return min(min(v.x, v.y), min(v.z, v.w)) == 0u; }
__device__ __forceinline__ uint4 nz4(uint32_t a, uint32_t b, uint32_t c, uint32_t d) { return make_uint4(max(a, 1u), max(b, 1u), max(c, 1u), max(d, 1u)); }
__device__ __forceinline__ void wait_flag(const uint32_t* p, uint32_t target) {
    int n = 0;
    while ((int)(ld_acquire(p) - target) < 0) { if (++n > SPIN_LIMIT) __trap(); }
}
__device__ __forceinline__ float silu_bf(uint32_t cbits) {
    const float c = __uint_as_float(cbits << 16);
    return bf_round(__fdividef(c, 1.f + fminf(ex2(-1.4426950408889634f * c), 1e30f)));
}
__device__ __forceinline__ void gemv_part(uint32_t wmbuf, int npanel, int wp, int lane) {
    const uint32_t wa = wmbuf + wp * 512 + (8 * (lane >> 4) + (lane & 7)) * 32 + ((lane >> 3) & 1) * 16;
    uint2 B[4];
#pragma unroll
    for (int i = 0; i < 4; i++) { const float2 v = lds2f(wmbuf + 28672 + (wp + 8 * i) * 32 + (lane & 3) * 8); B[i] = make_uint2(__float_as_uint(v.x), __float_as_uint(v.y)); }
#pragma unroll 1
    for (int pn = 0; pn < npanel; pn++) {
        float d[4] = {};
        uint32_t A[16];
#pragma unroll
        for (int i = 0; i < 4; i++) ldsm4t(wa + pn * 14336 + (i < 3 || wp < 4 ? i : 0) * 4096, A + 4 * i);
#pragma unroll
        for (int i = 0; i < 4; i++) mma16816(d, A[4 * i], A[4 * i + 1], A[4 * i + 2], A[4 * i + 3], B[i].x, B[i].y);
        if ((lane & 3) == 0) {
            sts1(wmbuf + 29696 + (wp * 32 + pn * 16 + (lane >> 2)) * 4, __float_as_uint(d[0]));
            sts1(wmbuf + 29696 + (wp * 32 + pn * 16 + 8 + (lane >> 2)) * 4, __float_as_uint(d[2]));
        }
    }
}
__device__ __forceinline__ void ln_coeffs(float mean, float msq, uint32_t& r2, uint32_t& n2) {
    const float rs = bf_round(rsqrtf(fmaxf(msq - mean * mean, 0.f) + 1e-5f));
    r2 = pack2(rs, rs);
    n2 = pack2(-mean * rs, -mean * rs);
}

__global__ void __cluster_dims__(2, 1, 1) __launch_bounds__(384, 1) fused_block_kernel(const __grid_constant__ Params p) {
    extern __shared__ __align__(1024) unsigned char smem[];
    const uint32_t sb = (uint32_t)__cvta_generic_to_shared(smem);
    const int tid = threadIdx.x, lane = tid & 31, warp = __shfl_sync(~0u, tid >> 5, 0);
    const int m = blockIdx.x >> 1;
#define kh (j & 1)
    int r, nq;
    {
        int g, i;
        if (m < MAP_S) { g = m < 4 ? 15 : 16; i = m & 3; }
        else if (m < MAP_S + 32) { g = (m - MAP_S) & 7; i = (m - MAP_S) >> 3; }
        else if (m < MAP_S + 60) { i = (m - MAP_S - 32) / 7; g = 8 + (m - MAP_S - 32) - 7 * i; }
        else { g = 16; i = m & 3; }
        r = g; nq = i;
    }
    const int j = opaque(2 * nq + (blockIdx.x & 1)), b = 8 * r + j, fs = 4 * kh + nq;
    const uint32_t sc = r == 16;
#define BAR(i) (sb + M_BAR + 8 * (i))
    if (lane == 0 && warp < 9 && warp != 6 && warp != 7) {
        const int i0 = warp == 8 ? 0 : 8 + 8 * warp, cnt = warp == 0 || warp == 8 ? 1 : warp < 3 ? 2 : 8;
#pragma unroll
        for (int k = 0; k < 8; k++) if (i0 + k != B_WMFULL) mbar_init(BAR(i0 + k), cnt);
        asm volatile("fence.mbarrier_init.release.cluster;" ::: "memory");
        fence_async_smem();
    }

    if (warp < 8) {
        const int w = warp >> 2, wi = warp & 3;
#define COORDS const int t = fresh_tid() & 127, lane = t & 31, q = lane & 3, lr = lane >> 2, ra = 64 * w + 16 * wi + lr; \
        const uint32_t lx = (lane >> 4) ^ (lane & 7), mrow = (64 * w + 16 * wi + ((lane >> 3) & 1) * 8 + (lane & 7)) * 128; \
        (void)q; (void)lr; (void)ra; (void)lx; (void)mrow;
        const int sid = 2 * (j & 3) + w;
#define RUN(k) (!sc || sid == (k))
#define WAIT(i, par) mbar_wait(BAR(i), (par) | sc)
        constexpr uint64_t DB128 = dconst(4096, 1024, 1);
        bar_arrive(9, 384);
        bar_sync(0, 384);
        asm volatile("barrier.cluster.arrive.relaxed.aligned;" ::: "memory");
        asm volatile("setmaxnreg.inc.sync.aligned.u32 224;");
        PROFC(0);
        uint32_t xr[16];
        {
            COORDS
            uint32_t h[112];
            if (RUN(0)) {
                float ds[4] = {}, da[2][4] = {}, db[2][4] = {};
                const uint32_t ONE2 = 0x3F803F80u;
                if (kh == 0) { WAIT(B_WMFULL, 0); gemv_part(sb + OFF_Y + HALF, 1, warp, lane); warp_arrive(BAR(B_GEMV)); }
#pragma unroll
                for (int kb = 0; kb < 7; kb++) {
                    WAIT(B_XFULL + kb, 0);
#pragma unroll
                    for (int k4 = 0; k4 < 4; k4++) ldsm4(sb + OFF_X + mrow + kb * 16384 + (((2 * k4) ^ lx) << 4), h + 16 * kb + 4 * k4);
#pragma unroll
                    for (int k4 = 0; k4 < 4; k4++) {
                        const uint32_t* f = h + 16 * kb + 4 * k4;
                        mma16816(ds, f[0], f[1], f[2], f[3], ONE2, ONE2);
                        mma1688(da[0], f[0], f[1], f[0]); mma1688(db[0], f[0], f[1], f[1]);
                        mma1688(da[1], f[2], f[3], f[2]); mma1688(db[1], f[2], f[3], f[3]);
                    }
                }
#pragma unroll
                for (int i = 0; i < 4; i++) {
                    const int ch = 7 * j + 2 * i + (lane >> 4);
                    ldsm4(sb + OFF_X + mrow + (ch >> 3) * 16384 + (((ch ^ lane) & 7) << 4), xr + 4 * i);
                }
                warp_arrive(BAR(B_XFREE));
                PROFC(27);
                float qa = (lr & 1) ? da[0][1] + da[1][1] : da[0][0] + da[1][0];
                float qb = (lr & 1) ? db[0][3] + db[1][3] : db[0][2] + db[1][2];
                const int src = (lane & ~3) | (lr >> 1);
                qa = __shfl_sync(~0u, qa, src);
                qb = __shfl_sync(~0u, qb, src);
                uint32_t ra2, na2, rb2, nb2;
                ln_coeffs(ds[0] * (1.f / DM), qa * (1.f / DM), ra2, na2);
                ln_coeffs(ds[2] * (1.f / DM), qb * (1.f / DM), rb2, nb2);
#pragma unroll
                for (int i = 0; i < 112; i += 2) { h[i] = hfma2(h[i], ra2, na2); h[i + 1] = hfma2(h[i + 1], rb2, nb2); }
                if (kh == 1) { WAIT(B_WMFULL, 0); gemv_part(sb + OFF_Y + HALF, 2, warp, lane); warp_arrive(BAR(B_GEMV)); }
            } else { reg_def<112>(h); reg_def<16>(xr); }
            PROFC(1);
            if (RUN(1)) {
                float ak[28], av[28], aq[28];
                uint32_t kp[14], vp[14];
                const uint64_t bk0 = mkdesc(sb + OFF_Y, DB128) + kh, bv0 = mkdesc(sb + OFF_Y + HALF, DB128) + kh, bq0 = mkdesc(sb + OFF_X, DB128) + kh;
                uint32_t* kvg = g_kv + (size_t)(b * 2) * 3584 + (8 * w + 2 * wi) * 224 + lane;
                WAIT(B_FULLK, 0);
                WAIT(B_MOD1, 0);
                PROFC(2);
                reg_def<28>(ak);
#pragma unroll
                for (int g4 = 0; g4 < 4; g4++) {
#pragma unroll
                    for (int ks = 7 * g4; ks < 7 * g4 + 7; ks++) {
                        const uint4 st = *(const uint4*)(smem + M_ST + ks * 64 + q * 16);
                        h[4 * ks] = hfma2(h[4 * ks], st.x, st.y); h[4 * ks + 1] = hfma2(h[4 * ks + 1], st.x, st.y);
                        h[4 * ks + 2] = hfma2(h[4 * ks + 2], st.z, st.w); h[4 * ks + 3] = hfma2(h[4 * ks + 3], st.z, st.w);
                    }
                    WG_FENCE();
#pragma unroll
                    for (int ks = 7 * g4; ks < 7 * g4 + 7; ks++) wgmma_rs_56<1>(ak, h[4 * ks], h[4 * ks + 1], h[4 * ks + 2], h[4 * ks + 3], bk0 + ks * 128, ks != 0);
                }
                WG_COMMIT();
                PROFC(3);
                WAIT(B_FULLV, 0);
                reg_def<28>(av);
                WG_FENCE();
#pragma unroll
                for (int ks = 0; ks < 8; ks++) wgmma_rs_56<1>(av, h[4 * ks], h[4 * ks + 1], h[4 * ks + 2], h[4 * ks + 3], bv0 + ks * 128, ks != 0);
                WG_COMMIT();
                WG_WAIT(1);
                reg_fence<28>(ak);
#pragma unroll
                for (int g = 0; g < 7; g++) {
                    kp[2 * g] = pack2(ak[4 * g], ak[4 * g + 1]); kp[2 * g + 1] = pack2(ak[4 * g + 2], ak[4 * g + 3]);
                    kvg[g * 32] = kp[2 * g]; kvg[224 + g * 32] = kp[2 * g + 1];
                }
                warp_arrive(BAR(B_PUB));
                PROFC(4);
                WG_FENCE();
#pragma unroll
                for (int ks = 8; ks < 28; ks++) wgmma_rs_56<1>(av, h[4 * ks], h[4 * ks + 1], h[4 * ks + 2], h[4 * ks + 3], bv0 + ks * 128, 1);
                WG_COMMIT();
                WAIT(B_FULLQ, 0);
                reg_def<28>(aq);
                WG_FENCE();
#pragma unroll
                for (int ks = 0; ks < 8; ks++) wgmma_rs_56<1>(aq, h[4 * ks], h[4 * ks + 1], h[4 * ks + 2], h[4 * ks + 3], bq0 + ks * 128, ks != 0);
                WG_COMMIT();
                WG_WAIT(1);
                reg_fence<28>(av);
#pragma unroll
                for (int g = 0; g < 7; g++) {
                    vp[2 * g] = pack2(av[4 * g], av[4 * g + 1]); vp[2 * g + 1] = pack2(av[4 * g + 2], av[4 * g + 3]);
                    kvg[3584 + g * 32] = vp[2 * g]; kvg[3584 + 224 + g * 32] = vp[2 * g + 1];
                }
                warp_arrive(BAR(B_PUB + 1));
                PROFC(5);
                WG_FENCE();
#pragma unroll
                for (int ks = 8; ks < 28; ks++) wgmma_rs_56<1>(aq, h[4 * ks], h[4 * ks + 1], h[4 * ks + 2], h[4 * ks + 3], bq0 + ks * 128, 1);
                WG_COMMIT();
                WAIT(B_PUB + 1, 0);
                const uint32_t ko = sb + OFF_Y + Y_KOWN + (8 * w + 2 * wi) * 896 + lane * 4;
                const uint32_t qo = sb + OFF_Y + Y_Q + (8 * w + 2 * wi) * 1024 + lane * 4;
#pragma unroll
                for (int g = 0; g < 7; g++) {
                    sts1(ko + g * 128, kp[2 * g]); sts1(ko + 896 + g * 128, kp[2 * g + 1]);
                    sts1(ko + (Y_VOWN - Y_KOWN) + g * 128, vp[2 * g]); sts1(ko + (Y_VOWN - Y_KOWN) + 896 + g * 128, vp[2 * g + 1]);
                }
                WG_WAIT(0);
                reg_fence<28>(aq);
                __syncwarp();
                if (lane < 3 && w == 1) mbar_arrive(BAR(B_EMPTY + lane));
#pragma unroll
                for (int g = 0; g < 7; g++) {
                    const uint32_t q0 = pack2(aq[4 * g], aq[4 * g + 1]), q1 = pack2(aq[4 * g + 2], aq[4 * g + 3]);
                    if (g == 3) {
                        sts1(qo + 3 * 128, q < 2 ? q0 : 0u); sts1(qo + 1024 + 3 * 128, q < 2 ? q1 : 0u);
                        sts1(qo + 4 * 128, q < 2 ? 0u : q0); sts1(qo + 1024 + 4 * 128, q < 2 ? 0u : q1);
                    } else {
                        const int ch = g < 3 ? g : g + 1;
                        sts1(qo + ch * 128, q0); sts1(qo + 1024 + ch * 128, q1);
                    }
                }
                if (!sc) bar_sync(3, 256);
            }
        }
        PROFC(6);
        WAIT(B_KRFULL, 0);
        PROFC(7);
        if (RUN(2)) {
#pragma unroll 1
            for (int hf = sc; hf < 2; hf++) {
                COORDS
                float s[136];
                float na = 0.f, nb = 0.f;
                const float CS = 0.18898223650461361f * 1.4426950408889634f;
                const int kg0 = 8 * hf + 2 * wi;
                const int pmin = 16 - 8 * r - 4 * hf - wi;
                const float NEG = __int_as_float(0xFF800000);
                {
                    uint32_t F[8];
                    const uint32_t qa = sb + OFF_Y + Y_Q + (kg0 + ((lane >> 3) & 1)) * 1024 + (4 * w + (lane >> 4)) * 128 + (lane & 7) * 16;
                    ldsm4(qa, F); ldsm4(qa + 256, F + 4);
                    uint32_t ka = sb + OFF_Y + Y_K + kg0 * 896 + (3 * w + (lane >> 3)) * 128 + (lane & 7) * 16;
#pragma unroll
                    for (int g = 0; g < 34; g++) {
                        uint32_t B[4];
                        if (g >= 12 && g % 4 == 0) ka += __float_as_uint(s[4 * (g - 12)]) & p.zero;
                        ldsm4(ka + g * 896, B);
                        mma16816_first(s + 4 * g, F[0], F[1], F[2], F[3], B[0], B[1]);
                        mma16816_v(s + 4 * g, F[4], F[5], F[6], F[7], B[2], B[3]);
                    }
                    const bool c0 = 2 * q > lr, c1 = 2 * q + 1 > lr;
                    if (!c0) { s[0] = NEG; s[6] = NEG; }
                    if (!c1) { s[1] = NEG; s[7] = NEG; }
                    s[2] = NEG; s[3] = NEG;
                    if (c0) { s[128] = NEG; s[134] = NEG; }
                    if (c1) { s[129] = NEG; s[135] = NEG; }
                    s[132] = NEG; s[133] = NEG;
                    float ma = NEG, mb = NEG;
#pragma unroll
                    for (int pp = 0; pp < 17; pp++) {
                        const float* e = s + 8 * pp;
                        const float bias = pp < pmin ? NEG : 0.f;
                        ma = fmaxf(ma, fmaxf(fmaxf(e[0], e[1]), fmaxf(e[4], e[5])) + bias);
                        mb = fmaxf(mb, fmaxf(fmaxf(e[2], e[3]), fmaxf(e[6], e[7])) + bias);
                    }
                    ma = fmaxf(ma, __shfl_xor_sync(~0u, ma, 1)); mb = fmaxf(mb, __shfl_xor_sync(~0u, mb, 1));
                    ma = fmaxf(ma, __shfl_xor_sync(~0u, ma, 2)); mb = fmaxf(mb, __shfl_xor_sync(~0u, mb, 2));
                    na = -ma * CS; nb = -mb * CS;
                }
                PROFC(8 + 3 * hf);
                {
                    if (hf == 0) mbar_wait(BAR(B_VRFULL), 0);
                    float o[16] = {}, rs[4] = {};
                    const uint32_t va = sb + OFF_Y + Y_VR + (kg0 + ((lane >> 3) & 1)) * 896 + (3 * w + (lane >> 4)) * 128 + (lane & 7) * 16;
#pragma unroll
                    for (int pp = 0; pp < 17; pp++) {
                        uint32_t B[8];
                        const uint32_t v = va + pp * 1792 + (pp == 16 || (pp >= 9 && kg0 + 2 * pp >= 32) ? Y_VOWN - 32 * 896 : 0);
                        ldsm4t(v, B); ldsm4t(v + 256, B + 4);
                        float e[8];
#pragma unroll
                        for (int i = 0; i < 8; i++) e[i] = ex2(fmaf(s[8 * pp + i], CS, ((i & 2) ? nb : na) + (pp < pmin ? NEG : 0.f)));
                        const uint32_t p0 = pack2(e[0], e[1]), p1 = pack2(e[2], e[3]), p2 = pack2(e[4], e[5]), p3 = pack2(e[6], e[7]);
                        mma16816(rs, p0, p1, p2, p3, 0x3F803F80u, 0x3F803F80u);
#pragma unroll
                        for (int g = 0; g < 4; g++) mma16816(o + 4 * g, p0, p1, p2, p3, B[2 * g], B[2 * g + 1]);
                    }
                    PROFC(9 + 3 * hf);
                    const float ia = rcp(rs[0]), ib = rcp(rs[2]);
                    uint32_t* og = g_o + (size_t)(2 * r + hf) * 14336 + (7 * j + 3 * w) * 256 + wi * 64 + lane;
#pragma unroll
                    for (int g = 0; g < 4; g++) {
                        if ((g == 3 - 3 * w) ? ((q >> 1) == w) : true) {
                            og[g * 256] = pack2(o[4 * g] * ia, o[4 * g + 1] * ia);
                            og[g * 256 + 32] = pack2(o[4 * g + 2] * ib, o[4 * g + 3] * ib);
                        }
                    }
                    warp_arrive(BAR(B_PUB + 2 + hf));
                    PROFC(10 + 3 * hf);
                }
            }
        }
        uint32_t x1p[14];
        COORDS
        constexpr uint64_t DT = dconst(1024, 128, 0);
        if (RUN(4)) {
            float ac[28];
            const uint64_t ad = mkdesc(sb + (w ? OFF_Y + HALF : OFF_X), DT), bd = mkdesc(sb + OFF_X + HALF, DB128) + kh;
            WAIT(B_WOFULL, 0);
            WAIT(B_MOD2, 0);
            WAIT(B_GFULL + w, 0);
            PROFC(28);
            reg_def<28>(ac);
#pragma unroll 1
            for (int u = 0; u < 4; u++) {
                WG_FENCE();
#pragma unroll
                for (int i = 0; i < 7; i++) wgmma_ss_56<1>(ac, ad + (7 * u + i) * 128, bd + (7 * u + i) * 128, (u | i) != 0);
            }
            WG_COMMIT();
            WG_WAIT(0);
            reg_fence<28>(ac);
            PROFC(14);
            __syncwarp();
            if (lane < 3) mbar_arrive(BAR(B_EMPTY + 4 + lane));
            if (lane < 3 && w == 0) mbar_arrive(BAR(B_EMPTY + lane));
            float s1a = 0.f, s2a = 0.f, s1b = 0.f, s2b = 0.f;
            uint32_t* xo = g_x1 + (size_t)(2 * r + w) * 14336 + 7 * j * 256 + wi * 64 + lane;
#pragma unroll
            for (int g = 0; g < 7; g++) {
                const float2 ga = *(const float2*)(smem + M_G + (8 * g + 2 * q) * 4);
                x1p[2 * g] = pack2(fmaf(ga.x, ac[4 * g], bf_lo(xr[2 * g])), fmaf(ga.y, ac[4 * g + 1], bf_hi(xr[2 * g])));
                x1p[2 * g + 1] = pack2(fmaf(ga.x, ac[4 * g + 2], bf_lo(xr[2 * g + 1])), fmaf(ga.y, ac[4 * g + 3], bf_hi(xr[2 * g + 1])));
                xo[g * 256] = x1p[2 * g]; xo[g * 256 + 32] = x1p[2 * g + 1];
                const float u0 = bf_lo(x1p[2 * g]), u1 = bf_hi(x1p[2 * g]), u2 = bf_lo(x1p[2 * g + 1]), u3 = bf_hi(x1p[2 * g + 1]);
                s1a += u0 + u1; s2a += u0 * u0 + u1 * u1; s1b += u2 + u3; s2b += u2 * u2 + u3 * u3;
            }
            float ka = (q & 1) ? s2a : s1a, kb2 = (q & 1) ? s2b : s1b;
            ka += __shfl_xor_sync(~0u, (q & 1) ? s1a : s2a, 1); kb2 += __shfl_xor_sync(~0u, (q & 1) ? s1b : s2b, 1);
            const float kk = ((q & 2) ? kb2 : ka) + __shfl_xor_sync(~0u, (q & 2) ? ka : kb2, 2);
            ((float*)g_st)[(((2 * r + w) * 8 + j) * 64 + 16 * wi + lr + 4 * (q & 2)) * 2 + (q & 1)] = kk;
            __syncwarp();
            if (lane < 2) mbar_arrive(BAR(B_PUB + 4 + w));
        } else reg_def<14>(x1p);
        PROFC(15);
        uint32_t h2a[32], h2b[24];
        if (RUN(6)) {
            const int fa = 224 * fs + ((fs & 1) ? 96 : 0), fb = 224 * fs + ((fs & 1) ? 0 : 128);
            uint32_t* h2g = g_h2 + (size_t)r * (224 * 512) + (8 * w + 2 * wi) * 32 + lane;
            const uint64_t a0 = mkdesc(sb + OFF_Y + w * HALF, DT);
            const int s0 = sc ? 12 : 0;
            {
                WAIT(B_GFULL + 2 + w, 0);
                PROFC(16);
                float2 sa = make_float2(0.f, 0.f), sbb = sa;
#pragma unroll
                for (int jj = 0; jj < 8; jj++) {
                    const float2 u = lds2f(sb + OFF_X + X_STAT + w * 4096 + (jj * 64 + 16 * wi + lr) * 8), v = lds2f(sb + OFF_X + X_STAT + w * 4096 + (jj * 64 + 16 * wi + lr + 8) * 8);
                    sa.x += u.x; sa.y += u.y; sbb.x += v.x; sbb.y += v.y;
                }
                warp_arrive(BAR(B_EMPTY + 3));
                uint32_t ra2, na2, rb2, nb2;
                ln_coeffs(sa.x * (1.f / DM), sa.y * (1.f / DM), ra2, na2);
                ln_coeffs(sbb.x * (1.f / DM), sbb.y * (1.f / DM), rb2, nb2);
                const uint32_t ha = sb + OFF_Y + w * HALF + (lane >> 4) * 1024 + (2 * wi + ((lane >> 3) & 1)) * 128 + (lane & 7) * 16;
                const uint32_t sta = sb + M_ST + q * 16;
                auto prep = [&](int s, uint32_t* f) {
#pragma unroll
                    for (int i = 0; i < 2; i++) {
                        uint32_t x[4];
                        ldsm4(ha + (2 * s + i) * 2048, x);
                        const uint4 st = lds4(sta + (2 * s + i) * 64);
                        f[4 * i] = hfma2(hfma2(x[0], ra2, na2), st.x, st.y); f[4 * i + 1] = hfma2(hfma2(x[1], rb2, nb2), st.x, st.y);
                        f[4 * i + 2] = hfma2(hfma2(x[2], ra2, na2), st.z, st.w); f[4 * i + 3] = hfma2(hfma2(x[3], rb2, nb2), st.z, st.w);
                        stsm4(ha + (2 * s + i) * 2048, f[4 * i], f[4 * i + 1], f[4 * i + 2], f[4 * i + 3]);
                    }
                };
                float ac[128];
                uint32_t fr[2][8];
                reg_def<128>(ac);
                prep(s0, fr[0]);
                PROFC(17);
                int sl = 0, prev = 0;
#pragma unroll 1
                for (int s2 = s0; s2 < 14; s2 += 2) {
#pragma unroll
                    for (int e = 0; e < 2; e++) {
                        const int s = s2 + e;
                        const uint32_t* f = fr[e];
                        WAIT(B_FULL + sl, s >= 7);
                        const uint64_t bd = mkdesc(sb + OFF_X + sl * 16384, DB128);
                        WG_FENCE();
                        wgmma_rs_256<1>(ac, f[0], f[1], f[2], f[3], bd, s != 0);
                        wgmma_rs_256<1>(ac, f[4], f[5], f[6], f[7], bd + 128, 1);
                        WG_COMMIT();
                        WG_WAIT(1);
                        if (s > 0) warp_arrive(BAR(B_EMPTY + prev));
                        if (s < 13) prep(s + 1, fr[e ^ 1]);
                        prev = sl; sl = sl == 6 ? 0 : sl + 1;
                    }
                }
                fence_async_smem();
                WG_WAIT(0);
                reg_fence<128>(ac);
                warp_arrive(BAR(B_EMPTY + 6));
                PROFC(18);
#pragma unroll
                for (int g = 0; g < 16; g++) {
                    h2a[2 * g] = hmul2(pack2_relu(ac[4 * g], ac[4 * g + 1]), pack2(ac[64 + 4 * g], ac[64 + 4 * g + 1]));
                    h2a[2 * g + 1] = hmul2(pack2_relu(ac[4 * g + 2], ac[4 * g + 3]), pack2(ac[64 + 4 * g + 2], ac[64 + 4 * g + 3]));
                    h2g[(fa / 8 + g) * 512] = h2a[2 * g]; h2g[(fa / 8 + g) * 512 + 32] = h2a[2 * g + 1];
                }
                warp_arrive(BAR(B_PUB + 6));
                bar_sync(1 + w, 128);
            }
            PROFC(19);
            {
                float ac[96];
                reg_def<96>(ac);
                int sl = 0, prev = 0;
#pragma unroll 1
                for (int s = s0; s < 14; s++) {
                    WAIT(B_FULL + sl, s >= 7);
                    const uint64_t ad = a0 + s * 256, bd = mkdesc(sb + OFF_X + sl * 16384, dconst(2048, 512, 2));
                    WG_FENCE();
                    wgmma_ss_192<1>(ac, ad, bd, s != 0);
                    wgmma_ss_192<1>(ac, ad + 128, bd + 64, 1);
                    WG_COMMIT();
                    if (s > 0) { WG_WAIT(1); warp_arrive(BAR(B_EMPTY + prev)); }
                    prev = sl; sl = sl == 6 ? 0 : sl + 1;
                }
                WG_WAIT(0);
                reg_fence<96>(ac);
                __syncwarp();
                if (lane < 6) mbar_arrive(BAR(B_EMPTY + 6 + lane));
                asm volatile("barrier.cluster.wait.aligned;" ::: "memory");
                if (lane == 0 && !sc) {
                    uint32_t rb;
                    asm volatile("mapa.shared::cluster.u32 %0, %1, %2;" : "=r"(rb) : "r"(BAR(B_PEER)), "r"(kh ^ 1));
                    asm volatile("mbarrier.arrive.relaxed.cluster.shared::cluster.b64 _, [%0];" ::"r"(rb) : "memory");
                }
                PROFC(20);
#pragma unroll
                for (int g = 0; g < 12; g++) {
                    h2b[2 * g] = hmul2(pack2_relu(ac[4 * g], ac[4 * g + 1]), pack2(ac[48 + 4 * g], ac[48 + 4 * g + 1]));
                    h2b[2 * g + 1] = hmul2(pack2_relu(ac[4 * g + 2], ac[4 * g + 3]), pack2(ac[48 + 4 * g + 2], ac[48 + 4 * g + 3]));
                    h2g[(fb / 8 + g) * 512] = h2b[2 * g]; h2g[(fb / 8 + g) * 512 + 32] = h2b[2 * g + 1];
                }
                warp_arrive(BAR(B_PUB + 7));
            }
        } else { reg_def<32>(h2a); reg_def<24>(h2b); }
        PROFC(21);
        if (RUN(7)) {
            float ac[56];
            reg_def<56>(ac);
            constexpr uint64_t DAN = dconst(2048, 128, 0);
#pragma unroll 1
            for (int u = 0; u < 12; u++) {
                WAIT(B_FULL + u, 0);
                const uint32_t sl = sb + u * 16384;
                const uint64_t ad = mkdesc(sl + 8192 + w * 1024, DAN), bd = mkdesc(sl, DB128);
                WG_FENCE();
                wgmma_ss_112<1>(ac, ad, bd, u != 0);
                wgmma_ss_112<1>(ac, ad + 256, bd + 128, 1);
                WG_COMMIT();
                if (u > 0) { WG_WAIT(1); warp_arrive(BAR(B_EMPTY + u - 1)); }
            }
            PROFC(22);
#pragma unroll
            for (int u = 0; u < 7; u++) {
                WAIT(B_FULL + u, 1);
                const uint64_t bd = mkdesc(sb + u * 16384, DB128);
                const uint32_t* hh = u < 4 ? h2a + 8 * u : h2b + 8 * (u - 4);
                WG_FENCE();
                wgmma_rs_112<1>(ac, hh[0], hh[1], hh[2], hh[3], bd, 1);
                wgmma_rs_112<1>(ac, hh[4], hh[5], hh[6], hh[7], bd + 128, 1);
                WG_COMMIT();
                if (u > 0 && u < 5) { WG_WAIT(1); warp_arrive(BAR(B_EMPTY + u - 1)); }
                if (u == 0) { WG_WAIT(1); warp_arrive(BAR(B_EMPTY + 11)); }
            }
            PROFC(23);
#pragma unroll 1
            for (int u = 7; u < 16; u++) {
                const int sli = u < 12 ? u : u - 12;
                WAIT(B_FULL + sli, u < 12);
                const uint32_t sl = sb + sli * 16384;
                const uint64_t ad = mkdesc(sl + 8192 + w * 1024, DAN), bd = mkdesc(sl, DB128);
                WG_FENCE();
                wgmma_ss_112<1>(ac, ad, bd, 1);
                wgmma_ss_112<1>(ac, ad + 256, bd + 128, 1);
                WG_COMMIT();
            }
            mbar_wait_cluster(BAR(B_PEER), sc);
            WG_WAIT(0);
            reg_fence<56>(ac);
            PROFC(24);
            uint32_t rdst, rbar;
            asm volatile("mapa.shared::cluster.u32 %0, %1, %2;" : "=r"(rdst) : "r"(sb + OFF_Y + (5 + w) * 16384 + t * 16), "r"(kh ^ 1 ^ sc));
            asm volatile("mapa.shared::cluster.u32 %0, %1, %2;" : "=r"(rbar) : "r"(BAR(B_XCH + w)), "r"(kh ^ 1 ^ sc));
#pragma unroll
            for (int g = 0; g < 7; g++) {
                const float v0 = kh ? ac[4 * g] : ac[28 + 4 * g], v1 = kh ? ac[4 * g + 1] : ac[28 + 4 * g + 1];
                const float v2 = kh ? ac[4 * g + 2] : ac[28 + 4 * g + 2], v3 = kh ? ac[4 * g + 3] : ac[28 + 4 * g + 3];
                if (!sc) asm volatile("st.async.shared::cluster.mbarrier::complete_tx::bytes.v4.f32 [%0], {%1,%2,%3,%4}, [%5];"
                             ::"r"(rdst + g * 2048), "f"(v0), "f"(v1), "f"(v2), "f"(v3), "r"(rbar) : "memory");
            }
            mbar_wait_cluster(BAR(B_XCH + w), sc);
            PROFC(25);
            bf16* og = (sc ? (bf16*)(g_h2 + 16 * 224 * 512) : p.out + (size_t)128 * r * DM) + (size_t)ra * DM + 56 * j + 2 * q;
#pragma unroll
            for (int g = 0; g < 7; g++) {
                const uint4 rv = *(const uint4*)(smem + OFF_Y + (5 + w) * 16384 + t * 16 + g * 2048);
                const float2 gb = *(const float2*)(smem + M_G + 224 + (8 * g + 2 * q) * 4);
                const float v0 = (kh ? ac[28 + 4 * g] : ac[4 * g]) + __uint_as_float(rv.x), v1 = (kh ? ac[28 + 4 * g + 1] : ac[4 * g + 1]) + __uint_as_float(rv.y);
                const float v2 = (kh ? ac[28 + 4 * g + 2] : ac[4 * g + 2]) + __uint_as_float(rv.z), v3 = (kh ? ac[28 + 4 * g + 3] : ac[4 * g + 3]) + __uint_as_float(rv.w);
                *(uint32_t*)(og + 8 * g) = pack2(fmaf(gb.x, v0, bf_lo(x1p[2 * g])), fmaf(gb.y, v1, bf_hi(x1p[2 * g])));
                *(uint32_t*)(og + 8 * DM + 8 * g) = pack2(fmaf(gb.x, v2, bf_lo(x1p[2 * g + 1])), fmaf(gb.y, v3, bf_hi(x1p[2 * g + 1])));
            }
        }
        PROFC(26);
        warp_arrive(BAR(B_DONE));
    } else {
        const int lane = fresh_tid() & 31;
        const bool early = kh == 0, gemv = r < 14;
        const int mcol = early ? 16 * (4 * r + nq) : 2 * DM + 32 * (4 * r + nq);
        const uint32_t wmbuf = sb + OFF_Y + HALF;
        const int fa = 224 * fs + ((fs & 1) ? 96 : 0), fb = 224 * fs + ((fs & 1) ? 0 : 128);
        asm volatile("setmaxnreg.dec.sync.aligned.u32 56;");
        if (warp == 9) {
#pragma unroll
            for (int i = 56; i < 63; i++) init_e(BAR(i), 1);
            fence_async_smem();
        }
        if (warp == 8) { init_e(BAR(B_WMFULL), 2); fence_async_smem(); }
        bar_arrive(0, 384);
        asm volatile("barrier.cluster.arrive.relaxed.aligned;" ::: "memory");
        uint32_t target = 0;
        if (warp == 8) {
            if (!sc) {
                expect_e(BAR(B_WMFULL), gemv ? 28672 >> early : 0);
                if (early && gemv) { tma3_e(wmbuf, &p.wm, mcol, 0, 0, BAR(B_WMFULL)); tma3_e(wmbuf + 7168, &p.wm, mcol, 224, 0, BAR(B_WMFULL)); }
#pragma unroll 1
                for (int kb = 0; kb < 7; kb++) {
                    expect_e(BAR(B_XFULL + kb), 16384);
                    tma3_e(sb + OFF_X + kb * 16384, &p.xm, 64 * kb, 128 * r, 0, BAR(B_XFULL + kb));
                }
            }
            PROFH(0);
#pragma unroll 1
            for (int mt = 0; mt < 4; mt++) {
                if (mt == 1) {
                    if (!early && gemv) {
#pragma unroll 1
                        for (int k = 0; k < 4; k++) tma3_e(wmbuf + k * 7168, &p.wm, mcol + (k >> 1) * 16, (k & 1) * 224, 0, BAR(B_WMFULL));
                    }
                    bar_sync(9, 384);
                    if (sc) return;
                    mbar_wait(BAR(B_MOD1), 0);
                    mbar_wait(BAR(B_WMFREE), 0);
                }
                if (mt == 2) mbar_wait(BAR(B_XFREE), 0);
                if (mt == 3) mbar_wait(BAR(B_VRFULL), 0);
                const uint32_t bar = BAR(mt == 3 ? B_WOFULL : B_FULLK + mt), dst = sb + (mt < 2 ? OFF_Y : OFF_X) + (mt & 1) * HALF;
                const int c0 = (mt < 2 ? DM + DM * mt : 0) + 56 * j - 8 * kh;
                if (!sc) {
                    expect_e(bar, HALF);
                    tma3_e(dst, mt == 3 ? &p.wo : &p.qkv, c0, 0, 0, bar);
                    tma3_e(dst + HALF / 2, mt == 3 ? &p.wo : &p.qkv, c0, 224, 0, bar);
                }
                if (mt & 1) PROFH(1 + (mt >> 1));
            }
            expect_e(BAR(B_XCH), 14336);
            expect_e(BAR(B_XCH + 1), 14336);
        } else {
            if (warp == 10 && lane == 0 && !sc) {
                const uint32_t ticket = atomicAdd(&g_ticket, 1u);
                l2_prefetch((const char*)p.wqkv + (size_t)b * 9408, 9408);
                sts1(sb + M_EPOCH, ticket / NCTA);
            }
            if (warp == 11) {
#pragma unroll
                for (int i = 0; i < 8; i++) {
                    const int wd = lane + 32 * i;
                    const uint32_t cb = i < 7 ? __ldg((const uint32_t*)p.c + wd) : 0u;
                    sts1(wmbuf + 28672 + (wd >> 3) * 32 + (wd & 3) * 8 + (wd & 4), pack2(silu_bf(cb & 0xFFFFu), silu_bf(cb >> 16)));
                }
            }
            bar_sync(9, 384);
            if (sc) return;
            target = lds1(sb + M_EPOCH) + 1;
            const uint32_t tag = target & 0xFFFFu;
            if (warp == 11) {
                warp_arrive(BAR(B_WMFULL));
                mbar_wait(BAR(B_GEMV), 0);
                float sum = 0.f;
#pragma unroll
                for (int i = 0; i < 8; i++) sum += *(const float*)(smem + OFF_Y + HALF + 29696 + (i * 32 + (early ? lane & 15 : lane)) * 4);
                const uint32_t word = (pack2(sum, 0.f) << 16) | tag;
                if (gemv) {
                    uint32_t* mg = g_mod + mcol + (early ? (lane & 15) + (lane >> 4) * 4 * 6 * DM : lane);
#pragma unroll
                    for (int i = 0; i < 8; i++) if (i < 4 || !early) st_relaxed(mg + i * 6 * DM, word);
                }
                warp_arrive(BAR(B_WMFREE));
                PROFH(5);
            }
            const uint4* modp = (const uint4*)g_mod + (r & 7) * (6 * DM / 4);
            const bool p2 = warp == 11;
            mbar_wait(BAR(p2 ? B_PUB : B_XFULL + 4), 0);
#pragma unroll 1
            for (int it = p2 ? 0 : warp - 9; it < (p2 ? 2 : warp - 8); it++) {
                const int i0 = lane + 32 * it, imax = p2 ? 251 : 223;
                uint4 v[4];
#pragma unroll 1
                for (int n = 0;; n++) {
                    uint32_t bad = 0;
#pragma unroll
                    for (int k = 0; k < 4; k++) {
                        const int i = min(i0 + 64 * k, imax);
                        v[k] = ld_relaxed4(modp + (i < 224 ? (p2 ? 336 : 0) + i : (i < 238 ? 14 * j + i : 14 * j + i + 322)));
                        bad |= (v[k].x ^ tag) | (v[k].y ^ tag) | (v[k].z ^ tag) | (v[k].w ^ tag);
                    }
                    if (!(bad & 0xFFFFu)) break;
                    if (n > SPIN_LIMIT) __trap();
                }
#pragma unroll
                for (int k = 0; k < 4; k++) {
                    const int i = min(i0 + 64 * k, imax);
                    if (i < 224) {
                        const int isc = i >= 112, c4 = i - 112 * isc;
                        const float one = isc ? 1.f : 0.f;
                        const uint32_t a = sb + M_ST + (c4 >> 2) * 64 + (c4 & 1) * 32 + (c4 & 2) * 4 + (isc ? 0 : 4);
                        sts1(a, pack2(bf_hi(v[k].x) + one, bf_hi(v[k].y) + one));
                        sts1(a + 16, pack2(bf_hi(v[k].z) + one, bf_hi(v[k].w) + one));
                    } else {
                        sts4(sb + M_G + (i - 224) * 16, make_uint4(v[k].x & 0xFFFF0000u, v[k].y & 0xFFFF0000u, v[k].z & 0xFFFF0000u, v[k].w & 0xFFFF0000u));
                    }
                }
                warp_arrive(BAR(p2 ? B_MOD2 : B_MOD1));
            }
            if (warp == 9) PROFH(6);
            if (warp == 9) {
#pragma unroll 1
                for (int kv = 0; kv < 2; kv++) {
                    mbar_wait(BAR(B_PUB + kv), 0);
                    if (lane >= 1 && lane <= 2 && r >= lane) wait_flag(g_flag + kv * 128 + b - 8 * lane, target);
                    __syncwarp();
                    fence_async_global();
                    const uint32_t dst = sb + OFF_Y + (kv ? Y_VR : Y_K);
                    expect_e(BAR(B_KRFULL + kv), r >= 2 ? 28672 : r == 1 ? 14336 : 0);
                    if (r >= 2) bulk_e(dst, g_kv + (size_t)((b - 16) * 2 + kv) * 3584, 14336, BAR(B_KRFULL + kv));
                    if (r >= 1) bulk_e(dst + 14336, g_kv + (size_t)((b - 8) * 2 + kv) * 3584, 14336, BAR(B_KRFULL + kv));
                    PROFH(7 + kv);
                }
            } else if (warp == 11) {
                mbar_wait(BAR(B_VRFULL), 0);
                if (lane == 0) {
                    l2_prefetch((const char*)p.wg + (size_t)b * 12544, 12544);
                    l2_prefetch((const char*)p.wu + (size_t)b * 12544, 12544);
                    l2_prefetch((const char*)p.wd + (size_t)b * 12544, 12544);
                }
                __syncwarp();
            }
        }
        if (warp == 8 || warp == 11) {
            const int sec = warp == 11;
            int sl = 0;
#pragma unroll 1
            for (int s = 0; s < 28; s++) {
                const bool pa = s < 14;
                const uint32_t half = pa ? 8192 : 6144;
                mbar_wait(BAR(B_EMPTY + sl), (s >= 7 && s < 14) || s >= 21);
                expect_e(BAR(B_FULL + sl), half);
                tma3_e(sb + OFF_X + sl * 16384 + sec * half, &p.ga + (pa ? 0 : 2) + sec, 0, 32 * (pa ? s : s - 14), pa ? fa >> 6 : fb >> 5, BAR(B_FULL + sl));
                sl = sl == 6 ? 0 : sl + 1;
            }
            if (!sec) PROFH(3);
            sl = 0;
            int u = 0;
#pragma unroll 1
            for (int grp = 0; grp < 8; grp++) {
                const bool pa = grp < 4, own = grp == 3 || grp == 4;
                int sidx = pa ? grp : grp - 5;
                sidx = own ? nq : sidx + (sidx >= nq);
                const int ofs = 4 * kh + sidx;
                int f = 224 * ofs + ((ofs & 1) ? (pa ? 96 : 0) : (pa ? 0 : 128));
                if (sec && (grp == 0 || grp == 5)) { mbar_wait(BAR(B_HRDY + !pa), 0); fence_async_global(); }
#pragma unroll 1
                for (int k = pa ? 0 : 1; k < 4; k++, u++, f += 32) {
                    const uint32_t dst = sb + sl * 16384, bar = BAR(B_FULL + sl);
                    mbar_wait(BAR(B_EMPTY + sl), u >= 12 && u < 24);
                    if (!sec) {
                        expect_e(bar, 8192);
                        tma3_e(dst, &p.dn, 0, nq, f, bar);
                        tma3_e(dst + 4096, &p.dn, 64, nq, f, bar);
                    } else {
                        expect_e(bar, own ? 0 : 8192);
                        if (!own) bulk_e(dst + 8192, g_h2 + (size_t)r * (224 * 512) + f * 64, 8192, bar);
                    }
                    sl = sl == 11 ? 0 : sl + 1;
                }
            }
            if (!sec) PROFH(4);
            mbar_wait(BAR(B_DONE), 0);
        } else if (warp == 9) {
#pragma unroll
            for (int ev = 0; ev < 4; ev++) expect_e(BAR(B_GFULL + ev), ev < 2 ? HALF : HALF + 4096);
            mbar_wait(BAR(B_PUB + 2), 0);
            uint32_t todo = ~0u;
#pragma unroll 1
            for (int n = 0; todo; n++) {
                if (todo == 0xFFFFFF00u) mbar_wait(BAR(B_PUB + 3), 0);
                uint32_t ok = __ballot_sync(~0u, (int)(ld_acquire(g_flag + (2 + (lane >> 3)) * 128 + 8 * r + (lane & 7)) - target) >= 0);
                uint32_t en = (ok >> j) & 0x01010101u;
                en &= (en << 8) | 0x0101u;
                en &= (en << 8) | 0x010101u;
                ok &= (en * 0xFFu) & todo;
                todo &= ~ok;
                fence_async_global();
#pragma unroll 1
                for (; ok; ok &= ok - 1) {
                    const int bit = __ffs(ok) - 1, ev = bit >> 3, jj = bit & 7, tile = 2 * r + (ev & 1);
                    const uint32_t bar = BAR(B_GFULL + ev);
                    bulk_e(sb + (ev == 0 ? OFF_X : OFF_Y + (ev & 1) * HALF) + jj * 7168, (ev < 2 ? g_o : g_x1) + (size_t)tile * 14336 + jj * 1792, 7168, bar);
                    if (ev >= 2) bulk_e(sb + OFF_X + X_STAT + (ev & 1) * 4096 + jj * 512, g_st + (tile * 8 + jj) * 64, 512, bar);
                }
                if (n > SPIN_LIMIT) __trap();
            }
#pragma unroll 1
            for (int ps = 0; ps < 2; ps++) {
                mbar_wait(BAR(B_PUB + 6 + ps), 0);
                if (lane < 4) wait_flag(g_flag + (6 + ps) * 128 + 8 * r + 2 * lane + kh, target);
                warp_arrive(BAR(B_HRDY + ps));
                PROFH(10 + ps);
            }
        } else {
            if (lane == 0) {
#pragma unroll 1
                for (int k = 0; k < 8; k++) {
                    mbar_wait(BAR(B_PUB + k), 0);
                    fence_gpu();
                    st_relaxed(g_flag + k * 128 + b, target);
                    if (k == 5) PROFH1(9);
                }
            }
        }
    }
}

typedef CUresult (*EncodeFn)(CUtensorMap*, CUtensorMapDataType, cuuint32_t, void*, const cuuint64_t*, const cuuint64_t*, const cuuint32_t*,
                             const cuuint32_t*, CUtensorMapInterleave, CUtensorMapSwizzle, CUtensorMapL2promotion, CUtensorMapFloatOOBfill);

static void make_map(EncodeFn fn, CUtensorMap* m, const void* ptr, uint64_t d0, uint64_t d1, uint64_t d2, uint64_t s1, uint64_t s2,
                     uint32_t b0, uint32_t b1, uint32_t b2, CUtensorMapSwizzle sw) {
    cuuint64_t dims[3] = {d0, d1, d2}, strides[2] = {s1, s2};
    cuuint32_t box[3] = {b0, b1, b2}, es[3] = {1, 1, 1};
    CUresult rc = fn(m, CU_TENSOR_MAP_DATA_TYPE_BFLOAT16, 3, (void*)ptr, dims, strides, box, es, CU_TENSOR_MAP_INTERLEAVE_NONE, sw,
                     CU_TENSOR_MAP_L2_PROMOTION_L2_128B, CU_TENSOR_MAP_FLOAT_OOB_FILL_NONE);
    (void)rc;
}

extern "C" void kernel_launch(void* const* d_in, const int* in_sizes, int n_in, void* d_out, int out_size) {
    (void)in_sizes; (void)n_in; (void)out_size;
    static EncodeFn fn = nullptr;
    if (!fn) {
        cudaDriverEntryPointQueryResult st;
        cudaGetDriverEntryPoint("cuTensorMapEncodeTiled", (void**)&fn, cudaEnableDefault, &st);
        cudaFuncSetAttribute(fused_block_kernel, cudaFuncAttributeMaxDynamicSharedMemorySize, SMEM_BYTES);
    }
    Params p;
    p.x = (const bf16*)d_in[0];
    const bf16* wqkv = (const bf16*)d_in[1];
    p.wqkv = wqkv;
    p.wop = (const bf16*)d_in[2];
    p.wg = (const bf16*)d_in[4];
    p.wu = (const bf16*)d_in[5];
    p.wd = (const bf16*)d_in[6];
    p.c = (const bf16*)d_in[7];
    p.wmod = (const bf16*)d_in[8];
    p.out = (bf16*)d_out;
    p.zero = 0;
    make_map(fn, &p.wm, p.wmod, 2688, 448, 1, 5376, 5376 * 448, 16, 224, 1, CU_TENSOR_MAP_SWIZZLE_NONE);
    make_map(fn, &p.xm, p.x, 448, 2048, 1, 896, 896 * 2048, 64, 128, 1, CU_TENSOR_MAP_SWIZZLE_128B);
    make_map(fn, &p.qkv, wqkv, 1344, 448, 1, 2688, 2688 * 448, 64, 224, 1, CU_TENSOR_MAP_SWIZZLE_128B);
    make_map(fn, &p.wo, p.wop, 448, 448, 1, 896, 896 * 448, 64, 224, 1, CU_TENSOR_MAP_SWIZZLE_128B);
    make_map(fn, &p.ga, p.wg, 64, 448, 28, 3584, 128, 64, 32, 2, CU_TENSOR_MAP_SWIZZLE_128B);
    make_map(fn, &p.ua, p.wu, 64, 448, 28, 3584, 128, 64, 32, 2, CU_TENSOR_MAP_SWIZZLE_128B);
    make_map(fn, &p.gb, p.wg, 32, 448, 56, 3584, 64, 32, 32, 3, CU_TENSOR_MAP_SWIZZLE_64B);
    make_map(fn, &p.ub, p.wu, 32, 448, 56, 3584, 64, 32, 32, 3, CU_TENSOR_MAP_SWIZZLE_64B);
    make_map(fn, &p.dn, p.wd, 112, 4, 1792, 224, 896, 64, 1, 32, CU_TENSOR_MAP_SWIZZLE_128B);
    fused_block_kernel<<<GRID, 384, SMEM_BYTES>>>(p);
}
```

```cpp
#include <cuda_runtime.h>
#include <cuda_bf16.h>
#include <cuda.h>
#include <stdint.h>

typedef __nv_bfloat16 bf16;

template<int TB> __device__ __forceinline__ void wgmma_rs_56(float* d, uint32_t a0, uint32_t a1, uint32_t a2, uint32_t a3, uint64_t db, int sd) {
  asm volatile("{\n.reg .pred p;\nsetp.ne.b32 p, %33, 0;\n"
    "wgmma.mma_async.sync.aligned.m64n56k16.f32.bf16.bf16 {%0,%1,%2,%3,%4,%5,%6,%7,%8,%9,%10,%11,%12,%13,%14,%15,%16,%17,%18,%19,%20,%21,%22,%23,%24,%25,%26,%27}, {%28,%29,%30,%31}, %32, p, 1, 1, %34;\n}\n"
    : "+f"(d[0]),"+f"(d[1]),"+f"(d[2]),"+f"(d[3]),"+f"(d[4]),"+f"(d[5]),"+f"(d[6]),"+f"(d[7]),"+f"(d[8]),"+f"(d[9]),"+f"(d[10]),"+f"(d[11]),"+f"(d[12]),"+f"(d[13]),"+f"(d[14]),"+f"(d[15]),"+f"(d[16]),"+f"(d[17]),"+f"(d[18]),"+f"(d[19]),"+f"(d[20]),"+f"(d[21]),"+f"(d[22]),"+f"(d[23]),"+f"(d[24]),"+f"(d[25]),"+f"(d[26]),"+f"(d[27])
    : "r"(a0), "r"(a1), "r"(a2), "r"(a3), "l"(db), "r"(sd), "n"(TB));
}
template<int TB> __device__ __forceinline__ void wgmma_ss_56(float* d, uint64_t da, uint64_t db, int sd) {
  asm volatile("{\n.reg .pred p;\nsetp.ne.b32 p, %30, 0;\n"
    "wgmma.mma_async.sync.aligned.m64n56k16.f32.bf16.bf16 {%0,%1,%2,%3,%4,%5,%6,%7,%8,%9,%10,%11,%12,%13,%14,%15,%16,%17,%18,%19,%20,%21,%22,%23,%24,%25,%26,%27}, %28, %29, p, 1, 1, 0, %31;\n}\n"
    : "+f"(d[0]),"+f"(d[1]),"+f"(d[2]),"+f"(d[3]),"+f"(d[4]),"+f"(d[5]),"+f"(d[6]),"+f"(d[7]),"+f"(d[8]),"+f"(d[9]),"+f"(d[10]),"+f"(d[11]),"+f"(d[12]),"+f"(d[13]),"+f"(d[14]),"+f"(d[15]),"+f"(d[16]),"+f"(d[17]),"+f"(d[18]),"+f"(d[19]),"+f"(d[20]),"+f"(d[21]),"+f"(d[22]),"+f"(d[23]),"+f"(d[24]),"+f"(d[25]),"+f"(d[26]),"+f"(d[27])
    : "l"(da), "l"(db), "r"(sd), "n"(TB));
}
template<int TB> __device__ __forceinline__ void wgmma_rs_256(float* d, uint32_t a0, uint32_t a1, uint32_t a2, uint32_t a3, uint64_t db, int sd) {
  asm volatile("{\n.reg .pred p;\nsetp.ne.b32 p, %133, 0;\n"
    "wgmma.mma_async.sync.aligned.m64n256k16.f32.bf16.bf16 {%0,%1,%2,%3,%4,%5,%6,%7,%8,%9,%10,%11,%12,%13,%14,%15,%16,%17,%18,%19,%20,%21,%22,%23,%24,%25,%26,%27,%28,%29,%30,%31,%32,%33,%34,%35,%36,%37,%38,%39,%40,%41,%42,%43,%44,%45,%46,%47,%48,%49,%50,%51,%52,%53,%54,%55,%56,%57,%58,%59,%60,%61,%62,%63,%64,%65,%66,%67,%68,%69,%70,%71,%72,%73,%74,%75,%76,%77,%78,%79,%80,%81,%82,%83,%84,%85,%86,%87,%88,%89,%90,%91,%92,%93,%94,%95,%96,%97,%98,%99,%100,%101,%102,%103,%104,%105,%106,%107,%108,%109,%110,%111,%112,%113,%114,%115,%116,%117,%118,%119,%120,%121,%122,%123,%124,%125,%126,%127}, {%128,%129,%130,%131}, %132, p, 1, 1, %134;\n}\n"
    : "+f"(d[0]),"+f"(d[1]),"+f"(d[2]),"+f"(d[3]),"+f"(d[4]),"+f"(d[5]),"+f"(d[6]),"+f"(d[7]),"+f"(d[8]),"+f"(d[9]),"+f"(d[10]),"+f"(d[11]),"+f"(d[12]),"+f"(d[13]),"+f"(d[14]),"+f"(d[15]),"+f"(d[16]),"+f"(d[17]),"+f"(d[18]),"+f"(d[19]),"+f"(d[20]),"+f"(d[21]),"+f"(d[22]),"+f"(d[23]),"+f"(d[24]),"+f"(d[25]),"+f"(d[26]),"+f"(d[27]),"+f"(d[28]),"+f"(d[29]),"+f"(d[30]),"+f"(d[31]),"+f"(d[32]),"+f"(d[33]),"+f"(d[34]),"+f"(d[35]),"+f"(d[36]),"+f"(d[37]),"+f"(d[38]),"+f"(d[39]),"+f"(d[40]),"+f"(d[41]),"+f"(d[42]),"+f"(d[43]),"+f"(d[44]),"+f"(d[45]),"+f"(d[46]),"+f"(d[47]),"+f"(d[48]),"+f"(d[49]),"+f"(d[50]),"+f"(d[51]),"+f"(d[52]),"+f"(d[53]),"+f"(d[54]),"+f"(d[55]),"+f"(d[56]),"+f"(d[57]),"+f"(d[58]),"+f"(d[59]),"+f"(d[60]),"+f"(d[61]),"+f"(d[62]),"+f"(d[63]),"+f"(d[64]),"+f"(d[65]),"+f"(d[66]),"+f"(d[67]),"+f"(d[68]),"+f"(d[69]),"+f"(d[70]),"+f"(d[71]),"+f"(d[72]),"+f"(d[73]),"+f"(d[74]),"+f"(d[75]),"+f"(d[76]),"+f"(d[77]),"+f"(d[78]),"+f"(d[79]),"+f"(d[80]),"+f"(d[81]),"+f"(d[82]),"+f"(d[83]),"+f"(d[84]),"+f"(d[85]),"+f"(d[86]),"+f"(d[87]),"+f"(d[88]),"+f"(d[89]),"+f"(d[90]),"+f"(d[91]),"+f"(d[92]),"+f"(d[93]),"+f"(d[94]),"+f"(d[95]),"+f"(d[96]),"+f"(d[97]),"+f"(d[98]),"+f"(d[99]),"+f"(d[100]),"+f"(d[101]),"+f"(d[102]),"+f"(d[103]),"+f"(d[104]),"+f"(d[105]),"+f"(d[106]),"+f"(d[107]),"+f"(d[108]),"+f"(d[109]),"+f"(d[110]),"+f"(d[111]),"+f"(d[112]),"+f"(d[113]),"+f"(d[114]),"+f"(d[115]),"+f"(d[116]),"+f"(d[117]),"+f"(d[118]),"+f"(d[119]),"+f"(d[120]),"+f"(d[121]),"+f"(d[122]),"+f"(d[123]),"+f"(d[124]),"+f"(d[125]),"+f"(d[126]),"+f"(d[127])
    : "r"(a0), "r"(a1), "r"(a2), "r"(a3), "l"(db), "r"(sd), "n"(TB));
}
template<int TB> __device__ __forceinline__ void wgmma_ss_192(float* d, uint64_t da, uint64_t db, int sd) {
  asm volatile("{\n.reg .pred p;\nsetp.ne.b32 p, %98, 0;\n"
    "wgmma.mma_async.sync.aligned.m64n192k16.f32.bf16.bf16 {%0,%1,%2,%3,%4,%5,%6,%7,%8,%9,%10,%11,%12,%13,%14,%15,%16,%17,%18,%19,%20,%21,%22,%23,%24,%25,%26,%27,%28,%29,%30,%31,%32,%33,%34,%35,%36,%37,%38,%39,%40,%41,%42,%43,%44,%45,%46,%47,%48,%49,%50,%51,%52,%53,%54,%55,%56,%57,%58,%59,%60,%61,%62,%63,%64,%65,%66,%67,%68,%69,%70,%71,%72,%73,%74,%75,%76,%77,%78,%79,%80,%81,%82,%83,%84,%85,%86,%87,%88,%89,%90,%91,%92,%93,%94,%95}, %96, %97, p, 1, 1, 0, %99;\n}\n"
    : "+f"(d[0]),"+f"(d[1]),"+f"(d[2]),"+f"(d[3]),"+f"(d[4]),"+f"(d[5]),"+f"(d[6]),"+f"(d[7]),"+f"(d[8]),"+f"(d[9]),"+f"(d[10]),"+f"(d[11]),"+f"(d[12]),"+f"(d[13]),"+f"(d[14]),"+f"(d[15]),"+f"(d[16]),"+f"(d[17]),"+f"(d[18]),"+f"(d[19]),"+f"(d[20]),"+f"(d[21]),"+f"(d[22]),"+f"(d[23]),"+f"(d[24]),"+f"(d[25]),"+f"(d[26]),"+f"(d[27]),"+f"(d[28]),"+f"(d[29]),"+f"(d[30]),"+f"(d[31]),"+f"(d[32]),"+f"(d[33]),"+f"(d[34]),"+f"(d[35]),"+f"(d[36]),"+f"(d[37]),"+f"(d[38]),"+f"(d[39]),"+f"(d[40]),"+f"(d[41]),"+f"(d[42]),"+f"(d[43]),"+f"(d[44]),"+f"(d[45]),"+f"(d[46]),"+f"(d[47]),"+f"(d[48]),"+f"(d[49]),"+f"(d[50]),"+f"(d[51]),"+f"(d[52]),"+f"(d[53]),"+f"(d[54]),"+f"(d[55]),"+f"(d[56]),"+f"(d[57]),"+f"(d[58]),"+f"(d[59]),"+f"(d[60]),"+f"(d[61]),"+f"(d[62]),"+f"(d[63]),"+f"(d[64]),"+f"(d[65]),"+f"(d[66]),"+f"(d[67]),"+f"(d[68]),"+f"(d[69]),"+f"(d[70]),"+f"(d[71]),"+f"(d[72]),"+f"(d[73]),"+f"(d[74]),"+f"(d[75]),"+f"(d[76]),"+f"(d[77]),"+f"(d[78]),"+f"(d[79]),"+f"(d[80]),"+f"(d[81]),"+f"(d[82]),"+f"(d[83]),"+f"(d[84]),"+f"(d[85]),"+f"(d[86]),"+f"(d[87]),"+f"(d[88]),"+f"(d[89]),"+f"(d[90]),"+f"(d[91]),"+f"(d[92]),"+f"(d[93]),"+f"(d[94]),"+f"(d[95])
    : "l"(da), "l"(db), "r"(sd), "n"(TB));
}
template<int TB> __device__ __forceinline__ void wgmma_ss_112(float* d, uint64_t da, uint64_t db, int sd) {
  asm volatile("{\n.reg .pred p;\nsetp.ne.b32 p, %58, 0;\n"
    "wgmma.mma_async.sync.aligned.m64n112k16.f32.bf16.bf16 {%0,%1,%2,%3,%4,%5,%6,%7,%8,%9,%10,%11,%12,%13,%14,%15,%16,%17,%18,%19,%20,%21,%22,%23,%24,%25,%26,%27,%28,%29,%30,%31,%32,%33,%34,%35,%36,%37,%38,%39,%40,%41,%42,%43,%44,%45,%46,%47,%48,%49,%50,%51,%52,%53,%54,%55}, %56, %57, p, 1, 1, 0, %59;\n}\n"
    : "+f"(d[0]),"+f"(d[1]),"+f"(d[2]),"+f"(d[3]),"+f"(d[4]),"+f"(d[5]),"+f"(d[6]),"+f"(d[7]),"+f"(d[8]),"+f"(d[9]),"+f"(d[10]),"+f"(d[11]),"+f"(d[12]),"+f"(d[13]),"+f"(d[14]),"+f"(d[15]),"+f"(d[16]),"+f"(d[17]),"+f"(d[18]),"+f"(d[19]),"+f"(d[20]),"+f"(d[21]),"+f"(d[22]),"+f"(d[23]),"+f"(d[24]),"+f"(d[25]),"+f"(d[26]),"+f"(d[27]),"+f"(d[28]),"+f"(d[29]),"+f"(d[30]),"+f"(d[31]),"+f"(d[32]),"+f"(d[33]),"+f"(d[34]),"+f"(d[35]),"+f"(d[36]),"+f"(d[37]),"+f"(d[38]),"+f"(d[39]),"+f"(d[40]),"+f"(d[41]),"+f"(d[42]),"+f"(d[43]),"+f"(d[44]),"+f"(d[45]),"+f"(d[46]),"+f"(d[47]),"+f"(d[48]),"+f"(d[49]),"+f"(d[50]),"+f"(d[51]),"+f"(d[52]),"+f"(d[53]),"+f"(d[54]),"+f"(d[55])
    : "l"(da), "l"(db), "r"(sd), "n"(TB));
}
template<int TB> __device__ __forceinline__ void wgmma_rs_112(float* d, uint32_t a0, uint32_t a1, uint32_t a2, uint32_t a3, uint64_t db, int sd) {
  asm volatile("{\n.reg .pred p;\nsetp.ne.b32 p, %61, 0;\n"
    "wgmma.mma_async.sync.aligned.m64n112k16.f32.bf16.bf16 {%0,%1,%2,%3,%4,%5,%6,%7,%8,%9,%10,%11,%12,%13,%14,%15,%16,%17,%18,%19,%20,%21,%22,%23,%24,%25,%26,%27,%28,%29,%30,%31,%32,%33,%34,%35,%36,%37,%38,%39,%40,%41,%42,%43,%44,%45,%46,%47,%48,%49,%50,%51,%52,%53,%54,%55}, {%56,%57,%58,%59}, %60, p, 1, 1, %62;\n}\n"
    : "+f"(d[0]),"+f"(d[1]),"+f"(d[2]),"+f"(d[3]),"+f"(d[4]),"+f"(d[5]),"+f"(d[6]),"+f"(d[7]),"+f"(d[8]),"+f"(d[9]),"+f"(d[10]),"+f"(d[11]),"+f"(d[12]),"+f"(d[13]),"+f"(d[14]),"+f"(d[15]),"+f"(d[16]),"+f"(d[17]),"+f"(d[18]),"+f"(d[19]),"+f"(d[20]),"+f"(d[21]),"+f"(d[22]),"+f"(d[23]),"+f"(d[24]),"+f"(d[25]),"+f"(d[26]),"+f"(d[27]),"+f"(d[28]),"+f"(d[29]),"+f"(d[30]),"+f"(d[31]),"+f"(d[32]),"+f"(d[33]),"+f"(d[34]),"+f"(d[35]),"+f"(d[36]),"+f"(d[37]),"+f"(d[38]),"+f"(d[39]),"+f"(d[40]),"+f"(d[41]),"+f"(d[42]),"+f"(d[43]),"+f"(d[44]),"+f"(d[45]),"+f"(d[46]),"+f"(d[47]),"+f"(d[48]),"+f"(d[49]),"+f"(d[50]),"+f"(d[51]),"+f"(d[52]),"+f"(d[53]),"+f"(d[54]),"+f"(d[55])
    : "r"(a0), "r"(a1), "r"(a2), "r"(a3), "l"(db), "r"(sd), "n"(TB));
}

constexpr int DM = 448;
constexpr int NCTA = 128;
#define MAPPING 1
#define GRID 132
#define PINGPONG 0
#define MAP_S 4
constexpr int SPIN_LIMIT = 1 << 22;

constexpr uint32_t OFF_X = 0, OFF_Y = 114688, OFF_MISC = 229376, SMEM_BYTES = 232448;
constexpr uint32_t Y_VR = 0, Y_K = 28672, Y_KOWN = 57344, Y_VOWN = 71680, Y_Q = 86016;
constexpr uint32_t HALF = 57344;
constexpr uint32_t M_BAR = OFF_MISC;
constexpr uint32_t M_ST = OFF_MISC + 512;
constexpr uint32_t M_G = OFF_MISC + 2304;
constexpr uint32_t M_EPOCH = OFF_MISC + 3040;
enum { B_XFULL = 0, B_FULLK = 7, B_FULLV = 8, B_FULLQ, B_KRFULL, B_VRFULL, B_WOFULL, B_XCH, B_FULL = 16, B_MOD1 = 28, B_MOD2, B_WMFULL,
       B_EMPTY = 32, B_XFREE = B_EMPTY + 12, B_GEMV, B_PEER, B_DONE,
       B_PUB = 48,
       B_WMFREE = 56, B_HRDY, B_GFULL = B_HRDY + 2 };
constexpr uint32_t X_STAT = 49152;

__device__ uint32_t g_ticket;
__device__ __align__(128) uint32_t g_mod[8 * 6 * DM];
__device__ __align__(128) uint32_t g_flag[8 * 16 * 8];
__device__ __align__(128) uint32_t g_kv[17 * 8 * 2 * 3584];
__device__ __align__(128) uint32_t g_ox[2 * 34 * 14336];
#define g_o g_ox
#define g_x1 (g_ox + 34 * 14336)
__device__ __align__(128) float2 g_st[34 * 8 * 64];
__device__ __align__(128) uint32_t g_h2[17 * 224 * 512];
#define PROFH(id)
#define PROFH1(id)
#define PROFC(id)

struct alignas(64) Params {
    CUtensorMap wm, xm, qkv, wo, ga, ua, gb, ub, dn;
    const bf16 *x, *c, *wqkv, *wmod, *wg, *wu, *wd, *wop;
    bf16* out;
    uint32_t zero;
};

__device__ __forceinline__ void mbar_init(uint32_t bar, int cnt) { asm volatile("mbarrier.init.shared::cta.b64 [%0], %1;" ::"r"(bar), "r"(cnt) : "memory"); }
__device__ __forceinline__ void mbar_expect_tx(uint32_t bar, uint32_t bytes) { asm volatile("mbarrier.arrive.expect_tx.shared::cta.b64 _, [%0], %1;" ::"r"(bar), "r"(bytes) : "memory"); }
__device__ __forceinline__ void mbar_arrive(uint32_t bar) { asm volatile("mbarrier.arrive.shared::cta.b64 _, [%0];" ::"r"(bar) : "memory"); }
__device__ __forceinline__ void mbar_wait(uint32_t bar, uint32_t parity) {
    uint32_t ok; int n = 0;
    do {
        asm volatile("{\n.reg .pred p;\nmbarrier.try_wait.parity.shared::cta.b64 p, [%1], %2;\nselp.u32 %0, 1, 0, p;\n}" : "=r"(ok) : "r"(bar), "r"(parity) : "memory");
        if (++n > SPIN_LIMIT) __trap();
    } while (!ok);
}
__device__ __forceinline__ void mbar_wait_cluster(uint32_t bar, uint32_t parity) {
    uint32_t ok; int n = 0;
    do {
        asm volatile("{\n.reg .pred p;\nmbarrier.try_wait.parity.acquire.cluster.shared::cta.b64 p, [%1], %2;\nselp.u32 %0, 1, 0, p;\n}" : "=r"(ok) : "r"(bar), "r"(parity) : "memory");
        if (++n > SPIN_LIMIT) __trap();
    } while (!ok);
}
__device__ __forceinline__ void warp_arrive(uint32_t bar) {
    __syncwarp();
    asm volatile("{\n.reg .pred p;\nelect.sync _|p, 0xffffffff;\n@p mbarrier.arrive.shared::cta.b64 _, [%0];\n}" ::"r"(bar) : "memory");
}
__device__ __forceinline__ int opaque(int v) { return __shfl_sync(~0u, v, 0); }
__device__ __forceinline__ int fresh_tid() { int v; asm volatile("mov.u32 %0, %%tid.x;" : "=r"(v)); return v; }
__device__ __forceinline__ void bar_sync(int id, int n) { asm volatile("bar.sync %0, %1;" ::"r"(id), "r"(n) : "memory"); }
__device__ __forceinline__ void bar_arrive(int id, int n) { asm volatile("bar.arrive %0, %1;" ::"r"(id), "r"(n) : "memory"); }
__device__ __forceinline__ void fence_async_smem() { asm volatile("fence.proxy.async.shared::cta;" ::: "memory"); }
__device__ __forceinline__ void fence_async_global() { asm volatile("fence.proxy.async.global;" ::: "memory"); }
__device__ __forceinline__ void fence_gpu() { asm volatile("fence.acq_rel.gpu;" ::: "memory"); }
__device__ __forceinline__ void tma3(uint32_t dst, const CUtensorMap* m, int c0, int c1, int c2, uint32_t bar) {
    asm volatile("cp.async.bulk.tensor.3d.shared::cluster.global.mbarrier::complete_tx::bytes [%0], [%1, {%3, %4, %5}], [%2];"
                 ::"r"(dst), "l"(m), "r"(bar), "r"(c0), "r"(c1), "r"(c2) : "memory");
}
__device__ __forceinline__ void bulk_load(uint32_t dst, const void* src, uint32_t bytes, uint32_t bar) {
    asm volatile("cp.async.bulk.shared::cluster.global.mbarrier::complete_tx::bytes [%0], [%1], %2, [%3];" ::"r"(dst), "l"(src), "r"(bytes), "r"(bar) : "memory");
}
__device__ __forceinline__ void expect_e(uint32_t bar, uint32_t bytes) {
    asm volatile("{\n.reg .pred p;\nelect.sync _|p, 0xffffffff;\n@p mbarrier.arrive.expect_tx.shared::cta.b64 _, [%0], %1;\n}" ::"r"(bar), "r"(bytes) : "memory");
}
__device__ __forceinline__ void tma3_e(uint32_t dst, const CUtensorMap* m, int c0, int c1, int c2, uint32_t bar) {
    asm volatile("{\n.reg .pred p;\nelect.sync _|p, 0xffffffff;\n@p cp.async.bulk.tensor.3d.shared::cluster.global.mbarrier::complete_tx::bytes [%0], [%1, {%3, %4, %5}], [%2];\n}"
                 ::"r"(dst), "l"(m), "r"(bar), "r"(c0), "r"(c1), "r"(c2) : "memory");
}
__device__ __forceinline__ void bulk_e(uint32_t dst, const void* src, uint32_t bytes, uint32_t bar) {
    asm volatile("{\n.reg .pred p;\nelect.sync _|p, 0xffffffff;\n@p cp.async.bulk.shared::cluster.global.mbarrier::complete_tx::bytes [%0], [%1], %2, [%3];\n}"
                 ::"r"(dst), "l"(src), "r"(bytes), "r"(bar) : "memory");
}
__device__ __forceinline__ void init_e(uint32_t bar, int cnt) {
    asm volatile("{\n.reg .pred p;\nelect.sync _|p, 0xffffffff;\n@p mbarrier.init.shared::cta.b64 [%0], %1;\n}" ::"r"(bar), "r"(cnt) : "memory");
}
__device__ __forceinline__ void l2_prefetch(const void* src, uint32_t bytes) { asm volatile("cp.async.bulk.prefetch.L2.global [%0], %1;" ::"l"(src), "r"(bytes) : "memory"); }
__device__ __forceinline__ uint32_t ld_relaxed(const uint32_t* p) { uint32_t v; asm volatile("ld.relaxed.gpu.global.u32 %0, [%1];" : "=r"(v) : "l"(p) : "memory"); return v; }
__device__ __forceinline__ void st_relaxed(uint32_t* p, uint32_t v) { asm volatile("st.relaxed.gpu.global.u32 [%0], %1;" ::"l"(p), "r"(v) : "memory"); }
__device__ __forceinline__ uint4 ld_relaxed4(const uint4* p) { uint4 v; asm volatile("ld.relaxed.gpu.global.v4.u32 {%0,%1,%2,%3}, [%4];" : "=r"(v.x), "=r"(v.y), "=r"(v.z), "=r"(v.w) : "l"(p) : "memory"); return v; }
__device__ __forceinline__ void st_relaxed4(uint4* p, uint4 v) { asm volatile("st.relaxed.gpu.global.v4.u32 [%0], {%1,%2,%3,%4};" ::"l"(p), "r"(v.x), "r"(v.y), "r"(v.z), "r"(v.w) : "memory"); }
__device__ __forceinline__ uint4 ldg_nc4(const void* p) { uint4 v; asm volatile("ld.global.nc.L1::no_allocate.v4.u32 {%0,%1,%2,%3}, [%4];" : "=r"(v.x), "=r"(v.y), "=r"(v.z), "=r"(v.w) : "l"(p)); return v; }
__device__ __forceinline__ uint32_t ldg_nc(const void* p) { uint32_t v; asm volatile("ld.global.nc.u32 %0, [%1];" : "=r"(v) : "l"(p)); return v; }
__device__ __forceinline__ uint32_t ld_acquire(const uint32_t* p) { uint32_t v; asm volatile("ld.acquire.gpu.global.u32 %0, [%1];" : "=r"(v) : "l"(p) : "memory"); return v; }
__device__ __forceinline__ uint4 lds4(uint32_t a) { uint4 v; asm volatile("ld.shared.v4.u32 {%0,%1,%2,%3}, [%4];" : "=r"(v.x), "=r"(v.y), "=r"(v.z), "=r"(v.w) : "r"(a) : "memory"); return v; }
__device__ __forceinline__ float2 lds2f(uint32_t a) { float2 v; asm volatile("ld.shared.v2.f32 {%0,%1}, [%2];" : "=f"(v.x), "=f"(v.y) : "r"(a) : "memory"); return v; }
__device__ __forceinline__ uint32_t lds1(uint32_t a) { uint32_t v; asm volatile("ld.shared.u32 %0, [%1];" : "=r"(v) : "r"(a) : "memory"); return v; }
__device__ __forceinline__ void sts4(uint32_t a, uint4 v) { asm volatile("st.shared.v4.u32 [%0], {%1,%2,%3,%4};" ::"r"(a), "r"(v.x), "r"(v.y), "r"(v.z), "r"(v.w) : "memory"); }
__device__ __forceinline__ void sts2(uint32_t a, uint32_t x, uint32_t y) { asm volatile("st.shared.v2.u32 [%0], {%1,%2};" ::"r"(a), "r"(x), "r"(y) : "memory"); }
__device__ __forceinline__ void sts1(uint32_t a, uint32_t v) { asm volatile("st.shared.u32 [%0], %1;" ::"r"(a), "r"(v) : "memory"); }
__device__ __forceinline__ void stsm4(uint32_t a, uint32_t r0, uint32_t r1, uint32_t r2, uint32_t r3) {
    asm volatile("stmatrix.sync.aligned.m8n8.x4.shared.b16 [%0], {%1,%2,%3,%4};" ::"r"(a), "r"(r0), "r"(r1), "r"(r2), "r"(r3));
}
__device__ __forceinline__ uint32_t pack2(float lo, float hi) { uint32_t r; asm("cvt.rn.bf16x2.f32 %0, %1, %2;" : "=r"(r) : "f"(hi), "f"(lo)); return r; }
__device__ __forceinline__ uint32_t pack2_relu(float lo, float hi) { uint32_t r; asm("cvt.rn.relu.bf16x2.f32 %0, %1, %2;" : "=r"(r) : "f"(hi), "f"(lo)); return r; }
__device__ __forceinline__ uint32_t hfma2(uint32_t a, uint32_t b, uint32_t c) { uint32_t r; asm("fma.rn.bf16x2 %0, %1, %2, %3;" : "=r"(r) : "r"(a), "r"(b), "r"(c)); return r; }
__device__ __forceinline__ uint32_t hmul2(uint32_t a, uint32_t b) { uint32_t r; asm("mul.rn.bf16x2 %0, %1, %2;" : "=r"(r) : "r"(a), "r"(b)); return r; }
__device__ __forceinline__ float bf_lo(uint32_t v) { return __uint_as_float(v << 16); }
__device__ __forceinline__ float bf_hi(uint32_t v) { return __uint_as_float(v & 0xFFFF0000u); }
__device__ __forceinline__ float bf_round(float v) { return bf_lo(pack2(v, 0.f)); }
__device__ __forceinline__ float ex2(float x) { float r; asm("ex2.approx.ftz.f32 %0, %1;" : "=f"(r) : "f"(x)); return r; }
__device__ __forceinline__ void mma16816(float* d, uint32_t a0, uint32_t a1, uint32_t a2, uint32_t a3, uint32_t b0, uint32_t b1) {
    asm("mma.sync.aligned.m16n8k16.row.col.f32.bf16.bf16.f32 {%0,%1,%2,%3}, {%4,%5,%6,%7}, {%8,%9}, {%0,%1,%2,%3};"
        : "+f"(d[0]), "+f"(d[1]), "+f"(d[2]), "+f"(d[3]) : "r"(a0), "r"(a1), "r"(a2), "r"(a3), "r"(b0), "r"(b1));
}
__device__ __forceinline__ void mma16816_first(float* d, uint32_t a0, uint32_t a1, uint32_t a2, uint32_t a3, uint32_t b0, uint32_t b1) {
    asm volatile("mma.sync.aligned.m16n8k16.row.col.f32.bf16.bf16.f32 {%0,%1,%2,%3}, {%4,%5,%6,%7}, {%8,%9}, {%10,%10,%10,%10};"
        : "=f"(d[0]), "=f"(d[1]), "=f"(d[2]), "=f"(d[3]) : "r"(a0), "r"(a1), "r"(a2), "r"(a3), "r"(b0), "r"(b1), "f"(0.f));
}
__device__ __forceinline__ void mma16816_v(float* d, uint32_t a0, uint32_t a1, uint32_t a2, uint32_t a3, uint32_t b0, uint32_t b1) {
    asm volatile("mma.sync.aligned.m16n8k16.row.col.f32.bf16.bf16.f32 {%0,%1,%2,%3}, {%4,%5,%6,%7}, {%8,%9}, {%0,%1,%2,%3};"
        : "+f"(d[0]), "+f"(d[1]), "+f"(d[2]), "+f"(d[3]) : "r"(a0), "r"(a1), "r"(a2), "r"(a3), "r"(b0), "r"(b1));
}
__device__ __forceinline__ void mma1688(float* d, uint32_t a0, uint32_t a1, uint32_t b0) {
    asm("mma.sync.aligned.m16n8k8.row.col.f32.bf16.bf16.f32 {%0,%1,%2,%3}, {%4,%5}, {%6}, {%0,%1,%2,%3};"
        : "+f"(d[0]), "+f"(d[1]), "+f"(d[2]), "+f"(d[3]) : "r"(a0), "r"(a1), "r"(b0));
}
__device__ __forceinline__ void ldsm4(uint32_t a, uint32_t* r) {
    asm volatile("ldmatrix.sync.aligned.m8n8.x4.shared.b16 {%0,%1,%2,%3}, [%4];" : "=r"(r[0]), "=r"(r[1]), "=r"(r[2]), "=r"(r[3]) : "r"(a));
}
__device__ __forceinline__ void ldsm4t(uint32_t a, uint32_t* r) {
    asm volatile("ldmatrix.sync.aligned.m8n8.x4.trans.shared.b16 {%0,%1,%2,%3}, [%4];" : "=r"(r[0]), "=r"(r[1]), "=r"(r[2]), "=r"(r[3]) : "r"(a));
}
__device__ __forceinline__ float rcp(float x) { float r; asm("rcp.approx.ftz.f32 %0, %1;" : "=f"(r) : "f"(x)); return r; }
__device__ __forceinline__ uint2 ld_relaxed2(const void* p) { uint2 v; asm volatile("ld.relaxed.gpu.global.v2.u32 {%0,%1}, [%2];" : "=r"(v.x), "=r"(v.y) : "l"(p) : "memory"); return v; }
__device__ __forceinline__ void st_relaxed2(void* p, uint32_t x, uint32_t y) { asm volatile("st.relaxed.gpu.global.v2.u32 [%0], {%1,%2};" ::"l"(p), "r"(max(x, 1u)), "r"(max(y, 1u)) : "memory"); }
__device__ __forceinline__ constexpr uint64_t dconst(uint32_t lbo, uint32_t sbo, uint32_t swz) {
    return ((uint64_t)(lbo >> 4) << 16) | ((uint64_t)(sbo >> 4) << 32) | ((uint64_t)swz << 62);
}
__device__ __forceinline__ uint64_t mkdesc(uint32_t addr, uint64_t c) { return c | (uint64_t)((addr & 0x3FFFF) >> 4); }
#define WG_FENCE() asm volatile("wgmma.fence.sync.aligned;" ::: "memory")
#define WG_COMMIT() asm volatile("wgmma.commit_group.sync.aligned;" ::: "memory")
#define WG_WAIT(n) asm volatile("wgmma.wait_group.sync.aligned %0;" ::"n"(n) : "memory")
template <int N> __device__ __forceinline__ void reg_fence(float* d) {
#pragma unroll
    for (int i = 0; i < N; i++) asm volatile("" : "+f"(d[i])::"memory");
}
template <int N> __device__ __forceinline__ void reg_def(float* d) {
#pragma unroll
    for (int i = 0; i < N; i++) asm volatile("" : "=f"(d[i]));
}
template <int N> __device__ __forceinline__ void reg_def(uint32_t* d) {
#pragma unroll
    for (int i = 0; i < N; i++) asm volatile("" : "=r"(d[i]));
}
__device__ __forceinline__ bool is_unset(uint4 v) { return min(min(v.x, v.y), min(v.z, v.w)) == 0u; }
__device__ __forceinline__ uint4 nz4(uint32_t a, uint32_t b, uint32_t c, uint32_t d) { return make_uint4(max(a, 1u), max(b, 1u), max(c, 1u), max(d, 1u)); }
__device__ __forceinline__ void wait_flag(const uint32_t* p, uint32_t target) {
    int n = 0;
    while ((int)(ld_acquire(p) - target) < 0) { if (++n > SPIN_LIMIT) __trap(); }
}
__device__ __forceinline__ float silu_bf(uint32_t cbits) {
    const float c = __uint_as_float(cbits << 16);
    return bf_round(__fdividef(c, 1.f + fminf(ex2(-1.4426950408889634f * c), 1e30f)));
}
__device__ __forceinline__ void gemv_part(uint32_t wmbuf, int npanel, int wp, int lane) {
    const uint32_t wa = wmbuf + wp * 512 + (8 * (lane >> 4) + (lane & 7)) * 32 + ((lane >> 3) & 1) * 16;
    uint2 B[4];
#pragma unroll
    for (int i = 0; i < 4; i++) { const float2 v = lds2f(wmbuf + 28672 + (wp + 8 * i) * 32 + (lane & 3) * 8); B[i] = make_uint2(__float_as_uint(v.x), __float_as_uint(v.y)); }
#pragma unroll 1
    for (int pn = 0; pn < npanel; pn++) {
        float d[4] = {};
        uint32_t A[16];
#pragma unroll
        for (int i = 0; i < 4; i++) ldsm4t(wa + pn * 14336 + (i < 3 || wp < 4 ? i : 0) * 4096, A + 4 * i);
#pragma unroll
        for (int i = 0; i < 4; i++) mma16816(d, A[4 * i], A[4 * i + 1], A[4 * i + 2], A[4 * i + 3], B[i].x, B[i].y);
        if ((lane & 3) == 0) {
            sts1(wmbuf + 29696 + (wp * 32 + pn * 16 + (lane >> 2)) * 4, __float_as_uint(d[0]));
            sts1(wmbuf + 29696 + (wp * 32 + pn * 16 + 8 + (lane >> 2)) * 4, __float_as_uint(d[2]));
        }
    }
}
__device__ __forceinline__ uint32_t slot_off(int l) { return (l < 3 || l > 6 ? l : l == 6 ? 3 : l + 1) * 16384; }
__device__ __forceinline__ void ln_coeffs(float mean, float msq, uint32_t& r2, uint32_t& n2) {
    const float rs = bf_round(rsqrtf(fmaxf(msq - mean * mean, 0.f) + 1e-5f));
    r2 = pack2(rs, rs);
    n2 = pack2(-mean * rs, -mean * rs);
}

__global__ void __cluster_dims__(2, 1, 1) __launch_bounds__(384, 1) fused_block_kernel(const __grid_constant__ Params p) {
    extern __shared__ __align__(1024) unsigned char smem[];
    const uint32_t sb = (uint32_t)__cvta_generic_to_shared(smem);
    const int tid = threadIdx.x, lane = tid & 31, warp = __shfl_sync(~0u, tid >> 5, 0);
    const int m = blockIdx.x >> 1;
#define kh (j & 1)
    int r, nq;
    {
        int g, i;
        if (m < MAP_S) { g = m < 4 ? 15 : 16; i = m & 3; }
        else if (m < MAP_S + 32) { g = (m - MAP_S) & 7; i = (m - MAP_S) >> 3; }
        else if (m < MAP_S + 60) { i = (m - MAP_S - 32) / 7; g = 8 + (m - MAP_S - 32) - 7 * i; }
        else { g = 16; i = m & 3; }
        r = g; nq = i;
    }
    const int j = opaque(2 * nq + (blockIdx.x & 1)), b = 8 * r + j, fs = 4 * kh + nq;
    const uint32_t sc = r == 16;
#define BAR(i) (sb + M_BAR + 8 * (i))
    if (lane == 0 && warp < 9 && warp != 6 && warp != 7) {
        const int i0 = warp == 8 ? 0 : 8 + 8 * warp, cnt = warp == 0 || warp == 8 ? 1 : warp < 3 ? 2 : 8;
#pragma unroll
        for (int k = 0; k < 8; k++) if (i0 + k != B_WMFULL) mbar_init(BAR(i0 + k), cnt);
        asm volatile("fence.mbarrier_init.release.cluster;" ::: "memory");
        fence_async_smem();
    }

    if (warp < 8) {
        const int w = warp >> 2, wi = warp & 3;
#define COORDS const int t = fresh_tid() & 127, lane = t & 31, q = lane & 3, lr = lane >> 2, ra = 64 * w + 16 * wi + lr; \
        const uint32_t lx = (lane >> 4) ^ (lane & 7), mrow = (64 * w + 16 * wi + ((lane >> 3) & 1) * 8 + (lane & 7)) * 128; \
        (void)q; (void)lr; (void)ra; (void)lx; (void)mrow;
        const int sid = 2 * (j & 3) + w;
#define RUN(k) (!sc || sid == (k))
#define WAIT(i, par) mbar_wait(BAR(i), (par) | sc)
        constexpr uint64_t DB128 = dconst(4096, 1024, 1);
        bar_arrive(9, 384);
        bar_sync(0, 384);
        asm volatile("barrier.cluster.arrive.relaxed.aligned;" ::: "memory");
        asm volatile("setmaxnreg.inc.sync.aligned.u32 224;");
        PROFC(0);
        uint32_t xr[16];
        {
            COORDS
            uint32_t h[112];
            if (RUN(0)) {
                float ds[4] = {}, da[2][4] = {}, db[2][4] = {};
                const uint32_t ONE2 = 0x3F803F80u;
                if (kh == 0) { WAIT(B_WMFULL, 0); gemv_part(sb + OFF_Y + HALF, 1, warp, lane); warp_arrive(BAR(B_GEMV)); }
#pragma unroll
                for (int kb = 0; kb < 7; kb++) {
                    WAIT(B_XFULL + kb, 0);
#pragma unroll
                    for (int k4 = 0; k4 < 4; k4++) ldsm4(sb + OFF_X + mrow + kb * 16384 + (((2 * k4) ^ lx) << 4), h + 16 * kb + 4 * k4);
#pragma unroll
                    for (int k4 = 0; k4 < 4; k4++) {
                        const uint32_t* f = h + 16 * kb + 4 * k4;
                        mma16816(ds, f[0], f[1], f[2], f[3], ONE2, ONE2);
                        mma1688(da[0], f[0], f[1], f[0]); mma1688(db[0], f[0], f[1], f[1]);
                        mma1688(da[1], f[2], f[3], f[2]); mma1688(db[1], f[2], f[3], f[3]);
                    }
                }
#pragma unroll
                for (int i = 0; i < 4; i++) {
                    const int ch = 7 * j + 2 * i + (lane >> 4);
                    ldsm4(sb + OFF_X + mrow + (ch >> 3) * 16384 + (((ch ^ lane) & 7) << 4), xr + 4 * i);
                }
                warp_arrive(BAR(B_XFREE));
                PROFC(27);
                float qa = (lr & 1) ? da[0][1] + da[1][1] : da[0][0] + da[1][0];
                float qb = (lr & 1) ? db[0][3] + db[1][3] : db[0][2] + db[1][2];
                const int src = (lane & ~3) | (lr >> 1);
                qa = __shfl_sync(~0u, qa, src);
                qb = __shfl_sync(~0u, qb, src);
                uint32_t ra2, na2, rb2, nb2;
                ln_coeffs(ds[0] * (1.f / DM), qa * (1.f / DM), ra2, na2);
                ln_coeffs(ds[2] * (1.f / DM), qb * (1.f / DM), rb2, nb2);
#pragma unroll
                for (int i = 0; i < 112; i += 2) { h[i] = hfma2(h[i], ra2, na2); h[i + 1] = hfma2(h[i + 1], rb2, nb2); }
                if (kh == 1) { WAIT(B_WMFULL, 0); gemv_part(sb + OFF_Y + HALF, 2, warp, lane); warp_arrive(BAR(B_GEMV)); }
            } else { reg_def<112>(h); reg_def<16>(xr); }
            PROFC(1);
            if (RUN(1)) {
                float ak[28], av[28], aq[28];
                uint32_t kp[14], vp[14];
                const uint64_t bk0 = mkdesc(sb + OFF_Y, DB128) + kh, bv0 = mkdesc(sb + OFF_Y + HALF, DB128) + kh, bq0 = mkdesc(sb + OFF_X, DB128) + kh;
                uint32_t* kvg = g_kv + (size_t)(b * 2) * 3584 + (8 * w + 2 * wi) * 224 + lane;
                WAIT(B_FULLK, 0);
                WAIT(B_MOD1, 0);
                PROFC(2);
                reg_def<28>(ak);
#pragma unroll
                for (int g4 = 0; g4 < 4; g4++) {
#pragma unroll
                    for (int ks = 7 * g4; ks < 7 * g4 + 7; ks++) {
                        const uint4 st = *(const uint4*)(smem + M_ST + ks * 64 + q * 16);
                        h[4 * ks] = hfma2(h[4 * ks], st.x, st.y); h[4 * ks + 1] = hfma2(h[4 * ks + 1], st.x, st.y);
                        h[4 * ks + 2] = hfma2(h[4 * ks + 2], st.z, st.w); h[4 * ks + 3] = hfma2(h[4 * ks + 3], st.z, st.w);
                    }
                    WG_FENCE();
#pragma unroll
                    for (int ks = 7 * g4; ks < 7 * g4 + 7; ks++) wgmma_rs_56<1>(ak, h[4 * ks], h[4 * ks + 1], h[4 * ks + 2], h[4 * ks + 3], bk0 + ks * 128, ks != 0);
                }
                WG_COMMIT();
                PROFC(3);
                WAIT(B_FULLV, 0);
                reg_def<28>(av);
                WG_FENCE();
#pragma unroll
                for (int ks = 0; ks < 8; ks++) wgmma_rs_56<1>(av, h[4 * ks], h[4 * ks + 1], h[4 * ks + 2], h[4 * ks + 3], bv0 + ks * 128, ks != 0);
                WG_COMMIT();
                WG_WAIT(1);
                reg_fence<28>(ak);
#pragma unroll
                for (int g = 0; g < 7; g++) {
                    kp[2 * g] = pack2(ak[4 * g], ak[4 * g + 1]); kp[2 * g + 1] = pack2(ak[4 * g + 2], ak[4 * g + 3]);
                    kvg[g * 32] = kp[2 * g]; kvg[224 + g * 32] = kp[2 * g + 1];
                }
                warp_arrive(BAR(B_PUB));
                PROFC(4);
                WG_FENCE();
#pragma unroll
                for (int ks = 8; ks < 28; ks++) wgmma_rs_56<1>(av, h[4 * ks], h[4 * ks + 1], h[4 * ks + 2], h[4 * ks + 3], bv0 + ks * 128, 1);
                WG_COMMIT();
                WAIT(B_FULLQ, 0);
                reg_def<28>(aq);
                WG_FENCE();
#pragma unroll
                for (int ks = 0; ks < 8; ks++) wgmma_rs_56<1>(aq, h[4 * ks], h[4 * ks + 1], h[4 * ks + 2], h[4 * ks + 3], bq0 + ks * 128, ks != 0);
                WG_COMMIT();
                WG_WAIT(1);
                reg_fence<28>(av);
#pragma unroll
                for (int g = 0; g < 7; g++) {
                    vp[2 * g] = pack2(av[4 * g], av[4 * g + 1]); vp[2 * g + 1] = pack2(av[4 * g + 2], av[4 * g + 3]);
                    kvg[3584 + g * 32] = vp[2 * g]; kvg[3584 + 224 + g * 32] = vp[2 * g + 1];
                }
                warp_arrive(BAR(B_PUB + 1));
                PROFC(5);
                WG_FENCE();
#pragma unroll
                for (int ks = 8; ks < 28; ks++) wgmma_rs_56<1>(aq, h[4 * ks], h[4 * ks + 1], h[4 * ks + 2], h[4 * ks + 3], bq0 + ks * 128, 1);
                WG_COMMIT();
                WAIT(B_PUB + 1, 0);
                const uint32_t ko = sb + OFF_Y + Y_KOWN + (8 * w + 2 * wi) * 896 + lane * 4;
                const uint32_t qo = sb + OFF_Y + Y_Q + (8 * w + 2 * wi) * 1024 + lane * 4;
#pragma unroll
                for (int g = 0; g < 7; g++) {
                    sts1(ko + g * 128, kp[2 * g]); sts1(ko + 896 + g * 128, kp[2 * g + 1]);
                    sts1(ko + (Y_VOWN - Y_KOWN) + g * 128, vp[2 * g]); sts1(ko + (Y_VOWN - Y_KOWN) + 896 + g * 128, vp[2 * g + 1]);
                }
                WG_WAIT(0);
                reg_fence<28>(aq);
                __syncwarp();
                if (lane < 3 && w == 1) mbar_arrive(BAR(B_EMPTY + lane));
#pragma unroll
                for (int g = 0; g < 7; g++) {
                    const uint32_t q0 = pack2(aq[4 * g], aq[4 * g + 1]), q1 = pack2(aq[4 * g + 2], aq[4 * g + 3]);
                    if (g == 3) {
                        sts1(qo + 3 * 128, q < 2 ? q0 : 0u); sts1(qo + 1024 + 3 * 128, q < 2 ? q1 : 0u);
                        sts1(qo + 4 * 128, q < 2 ? 0u : q0); sts1(qo + 1024 + 4 * 128, q < 2 ? 0u : q1);
                    } else {
                        const int ch = g < 3 ? g : g + 1;
                        sts1(qo + ch * 128, q0); sts1(qo + 1024 + ch * 128, q1);
                    }
                }
                if (!sc) bar_sync(3, 256);
            }
        }
        PROFC(6);
        WAIT(B_KRFULL, 0);
        PROFC(7);
        if (RUN(2)) {
#pragma unroll 1
            for (int hf = sc; hf < 2; hf++) {
                COORDS
                float s[136];
                float na = 0.f, nb = 0.f;
                const float CS = 0.18898223650461361f * 1.4426950408889634f;
                const int kg0 = 8 * hf + 2 * wi;
                const int pmin = 16 - 8 * r - 4 * hf - wi;
                const float NEG = __int_as_float(0xFF800000);
                {
                    uint32_t F[8];
                    const uint32_t qa = sb + OFF_Y + Y_Q + (kg0 + ((lane >> 3) & 1)) * 1024 + (4 * w + (lane >> 4)) * 128 + (lane & 7) * 16;
                    ldsm4(qa, F); ldsm4(qa + 256, F + 4);
                    uint32_t ka = sb + OFF_Y + Y_K + kg0 * 896 + (3 * w + (lane >> 3)) * 128 + (lane & 7) * 16;
#pragma unroll
                    for (int g = 0; g < 34; g++) {
                        uint32_t B[4];
                        if (g >= 12 && g % 4 == 0) ka += __float_as_uint(s[4 * (g - 12)]) & p.zero;
                        ldsm4(ka + g * 896, B);
                        mma16816_first(s + 4 * g, F[0], F[1], F[2], F[3], B[0], B[1]);
                        mma16816_v(s + 4 * g, F[4], F[5], F[6], F[7], B[2], B[3]);
                    }
                    const bool c0 = 2 * q > lr, c1 = 2 * q + 1 > lr;
                    if (!c0) { s[0] = NEG; s[6] = NEG; }
                    if (!c1) { s[1] = NEG; s[7] = NEG; }
                    s[2] = NEG; s[3] = NEG;
                    if (c0) { s[128] = NEG; s[134] = NEG; }
                    if (c1) { s[129] = NEG; s[135] = NEG; }
                    s[132] = NEG; s[133] = NEG;
                    float ma = NEG, mb = NEG;
#pragma unroll
                    for (int pp = 0; pp < 17; pp++) {
                        const float* e = s + 8 * pp;
                        const float bias = pp < pmin ? NEG : 0.f;
                        ma = fmaxf(ma, fmaxf(fmaxf(e[0], e[1]), fmaxf(e[4], e[5])) + bias);
                        mb = fmaxf(mb, fmaxf(fmaxf(e[2], e[3]), fmaxf(e[6], e[7])) + bias);
                    }
                    ma = fmaxf(ma, __shfl_xor_sync(~0u, ma, 1)); mb = fmaxf(mb, __shfl_xor_sync(~0u, mb, 1));
                    ma = fmaxf(ma, __shfl_xor_sync(~0u, ma, 2)); mb = fmaxf(mb, __shfl_xor_sync(~0u, mb, 2));
                    na = -ma * CS; nb = -mb * CS;
                }
                PROFC(8 + 3 * hf);
                {
                    if (hf == 0) mbar_wait(BAR(B_VRFULL), 0);
                    float o[16] = {}, rs[4] = {};
                    const uint32_t va = sb + OFF_Y + Y_VR + (kg0 + ((lane >> 3) & 1)) * 896 + (3 * w + (lane >> 4)) * 128 + (lane & 7) * 16;
#pragma unroll
                    for (int pp = 0; pp < 17; pp++) {
                        uint32_t B[8];
                        const uint32_t v = va + pp * 1792 + (pp == 16 || (pp >= 9 && kg0 + 2 * pp >= 32) ? Y_VOWN - 32 * 896 : 0);
                        ldsm4t(v, B); ldsm4t(v + 256, B + 4);
                        float e[8];
#pragma unroll
                        for (int i = 0; i < 8; i++) e[i] = ex2(fmaf(s[8 * pp + i], CS, ((i & 2) ? nb : na) + (pp < pmin ? NEG : 0.f)));
                        const uint32_t p0 = pack2(e[0], e[1]), p1 = pack2(e[2], e[3]), p2 = pack2(e[4], e[5]), p3 = pack2(e[6], e[7]);
                        mma16816(rs, p0, p1, p2, p3, 0x3F803F80u, 0x3F803F80u);
#pragma unroll
                        for (int g = 0; g < 4; g++) mma16816(o + 4 * g, p0, p1, p2, p3, B[2 * g], B[2 * g + 1]);
                    }
                    PROFC(9 + 3 * hf);
                    const float ia = rcp(rs[0]), ib = rcp(rs[2]);
                    uint32_t* og = g_o + (size_t)(2 * r + hf) * 14336 + (7 * j + 3 * w) * 256 + wi * 64 + lane;
#pragma unroll
                    for (int g = 0; g < 4; g++) {
                        if ((g == 3 - 3 * w) ? ((q >> 1) == w) : true) {
                            og[g * 256] = pack2(o[4 * g] * ia, o[4 * g + 1] * ia);
                            og[g * 256 + 32] = pack2(o[4 * g + 2] * ib, o[4 * g + 3] * ib);
                        }
                    }
                    warp_arrive(BAR(B_PUB + 2 + hf));
                    PROFC(10 + 3 * hf);
                }
            }
        }
        uint32_t x1p[14];
        COORDS
        constexpr uint64_t DT = dconst(1024, 128, 0);
        if (RUN(4)) {
            float ac[28];
            const uint64_t ad = mkdesc(sb + (w ? OFF_Y + HALF : OFF_X), DT), bd = mkdesc(sb + OFF_X + HALF, DB128) + kh;
            WAIT(B_WOFULL, 0);
            WAIT(B_MOD2, 0);
            WAIT(B_GFULL + w, 0);
            PROFC(28);
            reg_def<28>(ac);
#pragma unroll 1
            for (int u = 0; u < 4; u++) {
                WG_FENCE();
#pragma unroll
                for (int i = 0; i < 7; i++) wgmma_ss_56<1>(ac, ad + (7 * u + i) * 128, bd + (7 * u + i) * 128, (u | i) != 0);
            }
            WG_COMMIT();
            WG_WAIT(0);
            reg_fence<28>(ac);
            PROFC(14);
            __syncwarp();
            if (lane < 3) mbar_arrive(BAR(B_EMPTY + 3 + lane));
            if (lane < 3 && w == 0) mbar_arrive(BAR(B_EMPTY + lane));
            float s1a = 0.f, s2a = 0.f, s1b = 0.f, s2b = 0.f;
            uint32_t* xo = g_x1 + (size_t)(2 * r + w) * 14336 + 7 * j * 256 + wi * 64 + lane;
#pragma unroll
            for (int g = 0; g < 7; g++) {
                const float2 ga = *(const float2*)(smem + M_G + (8 * g + 2 * q) * 4);
                x1p[2 * g] = pack2(fmaf(ga.x, ac[4 * g], bf_lo(xr[2 * g])), fmaf(ga.y, ac[4 * g + 1], bf_hi(xr[2 * g])));
                x1p[2 * g + 1] = pack2(fmaf(ga.x, ac[4 * g + 2], bf_lo(xr[2 * g + 1])), fmaf(ga.y, ac[4 * g + 3], bf_hi(xr[2 * g + 1])));
                xo[g * 256] = x1p[2 * g]; xo[g * 256 + 32] = x1p[2 * g + 1];
                const float u0 = bf_lo(x1p[2 * g]), u1 = bf_hi(x1p[2 * g]), u2 = bf_lo(x1p[2 * g + 1]), u3 = bf_hi(x1p[2 * g + 1]);
                s1a += u0 + u1; s2a += u0 * u0 + u1 * u1; s1b += u2 + u3; s2b += u2 * u2 + u3 * u3;
            }
            float ka = (q & 1) ? s2a : s1a, kb2 = (q & 1) ? s2b : s1b;
            ka += __shfl_xor_sync(~0u, (q & 1) ? s1a : s2a, 1); kb2 += __shfl_xor_sync(~0u, (q & 1) ? s1b : s2b, 1);
            const float kk = ((q & 2) ? kb2 : ka) + __shfl_xor_sync(~0u, (q & 2) ? ka : kb2, 2);
            ((float*)g_st)[(((2 * r + w) * 8 + j) * 64 + 16 * wi + lr + 4 * (q & 2)) * 2 + (q & 1)] = kk;
            __syncwarp();
            if (lane < 2) mbar_arrive(BAR(B_PUB + 4 + w));
        } else reg_def<14>(x1p);
        PROFC(15);
        uint32_t h2a[32], h2b[24];
        if (RUN(6)) {
            const int fa = 224 * fs + ((fs & 1) ? 96 : 0), fb = 224 * fs + ((fs & 1) ? 0 : 128);
            uint32_t* h2g = g_h2 + (size_t)r * (224 * 512) + (8 * w + 2 * wi) * 32 + lane;
            const uint64_t a0 = mkdesc(sb + OFF_Y + w * HALF, DT);
            const int s0 = sc ? 12 : 0;
            {
                WAIT(B_GFULL + 2 + w, 0);
                PROFC(16);
                float2 sa = make_float2(0.f, 0.f), sbb = sa;
#pragma unroll
                for (int jj = 0; jj < 8; jj++) {
                    const float2 u = lds2f(sb + OFF_X + X_STAT + w * 4096 + (jj * 64 + 16 * wi + lr) * 8), v = lds2f(sb + OFF_X + X_STAT + w * 4096 + (jj * 64 + 16 * wi + lr + 8) * 8);
                    sa.x += u.x; sa.y += u.y; sbb.x += v.x; sbb.y += v.y;
                }
                warp_arrive(BAR(B_EMPTY + 6));
                uint32_t ra2, na2, rb2, nb2;
                ln_coeffs(sa.x * (1.f / DM), sa.y * (1.f / DM), ra2, na2);
                ln_coeffs(sbb.x * (1.f / DM), sbb.y * (1.f / DM), rb2, nb2);
                const uint32_t ha = sb + OFF_Y + w * HALF + (lane >> 4) * 1024 + (2 * wi + ((lane >> 3) & 1)) * 128 + (lane & 7) * 16;
                const uint32_t sta = sb + M_ST + q * 16;
                auto prep = [&](int s, uint32_t* f) {
#pragma unroll
                    for (int i = 0; i < 2; i++) {
                        uint32_t x[4];
                        ldsm4(ha + (2 * s + i) * 2048, x);
                        const uint4 st = lds4(sta + (2 * s + i) * 64);
                        f[4 * i] = hfma2(hfma2(x[0], ra2, na2), st.x, st.y); f[4 * i + 1] = hfma2(hfma2(x[1], rb2, nb2), st.x, st.y);
                        f[4 * i + 2] = hfma2(hfma2(x[2], ra2, na2), st.z, st.w); f[4 * i + 3] = hfma2(hfma2(x[3], rb2, nb2), st.z, st.w);
                        stsm4(ha + (2 * s + i) * 2048, f[4 * i], f[4 * i + 1], f[4 * i + 2], f[4 * i + 3]);
                    }
                };
                float ac[128];
                uint32_t fr[2][8];
                reg_def<128>(ac);
                prep(s0, fr[0]);
                PROFC(17);
                int sl = 0, prev = 0;
#pragma unroll 1
                for (int s2 = s0; s2 < 14; s2 += 2) {
#pragma unroll
                    for (int e = 0; e < 2; e++) {
                        const int s = s2 + e;
                        const uint32_t* f = fr[e];
                        WAIT(B_FULL + sl, s >= 7);
                        const uint64_t bd = mkdesc(sb + slot_off(sl), DB128);
                        WG_FENCE();
                        wgmma_rs_256<1>(ac, f[0], f[1], f[2], f[3], bd, s != 0);
                        wgmma_rs_256<1>(ac, f[4], f[5], f[6], f[7], bd + 128, 1);
                        WG_COMMIT();
                        WG_WAIT(1);
                        if (s > 0) warp_arrive(BAR(B_EMPTY + prev));
                        if (s < 13) prep(s + 1, fr[e ^ 1]);
                        prev = sl; sl = sl == 6 ? 0 : sl + 1;
                    }
                }
                fence_async_smem();
                WG_WAIT(0);
                reg_fence<128>(ac);
                warp_arrive(BAR(B_EMPTY + 6));
                PROFC(18);
#pragma unroll
                for (int g = 0; g < 16; g++) {
                    h2a[2 * g] = hmul2(pack2_relu(ac[4 * g], ac[4 * g + 1]), pack2(ac[64 + 4 * g], ac[64 + 4 * g + 1]));
                    h2a[2 * g + 1] = hmul2(pack2_relu(ac[4 * g + 2], ac[4 * g + 3]), pack2(ac[64 + 4 * g + 2], ac[64 + 4 * g + 3]));
                    h2g[(fa / 8 + g) * 512] = h2a[2 * g]; h2g[(fa / 8 + g) * 512 + 32] = h2a[2 * g + 1];
                }
                warp_arrive(BAR(B_PUB + 6));
                bar_sync(1 + w, 128);
            }
            PROFC(19);
            {
                float ac[96];
                reg_def<96>(ac);
                int sl = 0, prev = 0;
#pragma unroll 1
                for (int s = s0; s < 14; s++) {
                    WAIT(B_FULL + sl, s >= 7);
                    const uint64_t ad = a0 + s * 256, bd = mkdesc(sb + slot_off(sl), dconst(2048, 512, 2));
                    WG_FENCE();
                    wgmma_ss_192<1>(ac, ad, bd, s != 0);
                    wgmma_ss_192<1>(ac, ad + 128, bd + 64, 1);
                    WG_COMMIT();
                    if (s > 0) { WG_WAIT(1); warp_arrive(BAR(B_EMPTY + prev)); }
                    prev = sl; sl = sl == 6 ? 0 : sl + 1;
                }
                WG_WAIT(0);
                reg_fence<96>(ac);
                __syncwarp();
                if (lane < 6) mbar_arrive(BAR(B_EMPTY + 6 + lane));
                asm volatile("barrier.cluster.wait.aligned;" ::: "memory");
                if (lane == 0 && !sc) {
                    uint32_t rb;
                    asm volatile("mapa.shared::cluster.u32 %0, %1, %2;" : "=r"(rb) : "r"(BAR(B_PEER)), "r"(kh ^ 1));
                    asm volatile("mbarrier.arrive.relaxed.cluster.shared::cluster.b64 _, [%0];" ::"r"(rb) : "memory");
                }
                PROFC(20);
#pragma unroll
                for (int g = 0; g < 12; g++) {
                    h2b[2 * g] = hmul2(pack2_relu(ac[4 * g], ac[4 * g + 1]), pack2(ac[48 + 4 * g], ac[48 + 4 * g + 1]));
                    h2b[2 * g + 1] = hmul2(pack2_relu(ac[4 * g + 2], ac[4 * g + 3]), pack2(ac[48 + 4 * g + 2], ac[48 + 4 * g + 3]));
                    h2g[(fb / 8 + g) * 512] = h2b[2 * g]; h2g[(fb / 8 + g) * 512 + 32] = h2b[2 * g + 1];
                }
                warp_arrive(BAR(B_PUB + 7));
            }
        } else { reg_def<32>(h2a); reg_def<24>(h2b); }
        PROFC(21);
        if (RUN(7)) {
            float ac[56];
            reg_def<56>(ac);
            constexpr uint64_t DAN = dconst(2048, 128, 0);
#pragma unroll 1
            for (int u = 0; u < 12; u++) {
                WAIT(B_FULL + u, 0);
                const uint32_t sl = sb + slot_off(u);
                const uint64_t ad = mkdesc(sl + 8192 + w * 1024, DAN), bd = mkdesc(sl, DB128);
                WG_FENCE();
                wgmma_ss_112<1>(ac, ad, bd, u != 0);
                wgmma_ss_112<1>(ac, ad + 256, bd + 128, 1);
                WG_COMMIT();
                if (u > 0) { WG_WAIT(1); warp_arrive(BAR(B_EMPTY + u - 1)); }
            }
            PROFC(22);
#pragma unroll
            for (int u = 0; u < 7; u++) {
                WAIT(B_FULL + u, 1);
                const uint64_t bd = mkdesc(sb + slot_off(u), DB128);
                const uint32_t* hh = u < 4 ? h2a + 8 * u : h2b + 8 * (u - 4);
                WG_FENCE();
                wgmma_rs_112<1>(ac, hh[0], hh[1], hh[2], hh[3], bd, 1);
                wgmma_rs_112<1>(ac, hh[4], hh[5], hh[6], hh[7], bd + 128, 1);
                WG_COMMIT();
                if (u > 0 && u < 5) { WG_WAIT(1); warp_arrive(BAR(B_EMPTY + u - 1)); }
                if (u == 0) { WG_WAIT(1); warp_arrive(BAR(B_EMPTY + 11)); }
            }
            PROFC(23);
#pragma unroll 1
            for (int u = 7; u < 16; u++) {
                const int sli = u < 12 ? u : u - 12;
                WAIT(B_FULL + sli, u < 12);
                const uint32_t sl = sb + slot_off(sli);
                const uint64_t ad = mkdesc(sl + 8192 + w * 1024, DAN), bd = mkdesc(sl, DB128);
                WG_FENCE();
                wgmma_ss_112<1>(ac, ad, bd, 1);
                wgmma_ss_112<1>(ac, ad + 256, bd + 128, 1);
                WG_COMMIT();
            }
            mbar_wait_cluster(BAR(B_PEER), sc);
            WG_WAIT(0);
            reg_fence<56>(ac);
            PROFC(24);
            uint32_t rdst, rbar;
            asm volatile("mapa.shared::cluster.u32 %0, %1, %2;" : "=r"(rdst) : "r"(sb + OFF_Y + (5 + w) * 16384 + t * 16), "r"(kh ^ 1 ^ sc));
            asm volatile("mapa.shared::cluster.u32 %0, %1, %2;" : "=r"(rbar) : "r"(BAR(B_XCH + w)), "r"(kh ^ 1 ^ sc));
#pragma unroll
            for (int g = 0; g < 7; g++) {
                const float v0 = kh ? ac[4 * g] : ac[28 + 4 * g], v1 = kh ? ac[4 * g + 1] : ac[28 + 4 * g + 1];
                const float v2 = kh ? ac[4 * g + 2] : ac[28 + 4 * g + 2], v3 = kh ? ac[4 * g + 3] : ac[28 + 4 * g + 3];
                if (!sc) asm volatile("st.async.shared::cluster.mbarrier::complete_tx::bytes.v4.f32 [%0], {%1,%2,%3,%4}, [%5];"
                             ::"r"(rdst + g * 2048), "f"(v0), "f"(v1), "f"(v2), "f"(v3), "r"(rbar) : "memory");
            }
            mbar_wait_cluster(BAR(B_XCH + w), sc);
            PROFC(25);
            bf16* og = (sc ? (bf16*)(g_h2 + 16 * 224 * 512) : p.out + (size_t)128 * r * DM) + (size_t)ra * DM + 56 * j + 2 * q;
#pragma unroll
            for (int g = 0; g < 7; g++) {
                const uint4 rv = *(const uint4*)(smem + OFF_Y + (5 + w) * 16384 + t * 16 + g * 2048);
                const float2 gb = *(const float2*)(smem + M_G + 224 + (8 * g + 2 * q) * 4);
                const float v0 = (kh ? ac[28 + 4 * g] : ac[4 * g]) + __uint_as_float(rv.x), v1 = (kh ? ac[28 + 4 * g + 1] : ac[4 * g + 1]) + __uint_as_float(rv.y);
                const float v2 = (kh ? ac[28 + 4 * g + 2] : ac[4 * g + 2]) + __uint_as_float(rv.z), v3 = (kh ? ac[28 + 4 * g + 3] : ac[4 * g + 3]) + __uint_as_float(rv.w);
                *(uint32_t*)(og + 8 * g) = pack2(fmaf(gb.x, v0, bf_lo(x1p[2 * g])), fmaf(gb.y, v1, bf_hi(x1p[2 * g])));
                *(uint32_t*)(og + 8 * DM + 8 * g) = pack2(fmaf(gb.x, v2, bf_lo(x1p[2 * g + 1])), fmaf(gb.y, v3, bf_hi(x1p[2 * g + 1])));
            }
        }
        PROFC(26);
        warp_arrive(BAR(B_DONE));
    } else {
        const int lane = fresh_tid() & 31;
        const bool early = kh == 0, gemv = r < 14;
        const int mcol = early ? 16 * (4 * r + nq) : 2 * DM + 32 * (4 * r + nq);
        const uint32_t wmbuf = sb + OFF_Y + HALF;
        const int fa = 224 * fs + ((fs & 1) ? 96 : 0), fb = 224 * fs + ((fs & 1) ? 0 : 128);
        asm volatile("setmaxnreg.dec.sync.aligned.u32 56;");
        if (warp == 9) {
#pragma unroll
            for (int i = 56; i < 63; i++) init_e(BAR(i), 1);
            fence_async_smem();
        }
        if (warp == 8) { init_e(BAR(B_WMFULL), 2); fence_async_smem(); }
        bar_arrive(0, 384);
        asm volatile("barrier.cluster.arrive.relaxed.aligned;" ::: "memory");
        uint32_t target = 0;
        if (warp == 8) {
            if (!sc) {
                expect_e(BAR(B_WMFULL), gemv ? 28672 >> early : 0);
                if (early && gemv) { tma3_e(wmbuf, &p.wm, mcol, 0, 0, BAR(B_WMFULL)); tma3_e(wmbuf + 7168, &p.wm, mcol, 224, 0, BAR(B_WMFULL)); }
#pragma unroll 1
                for (int kb = 0; kb < 7; kb++) {
                    expect_e(BAR(B_XFULL + kb), 16384);
                    tma3_e(sb + OFF_X + kb * 16384, &p.xm, 64 * kb, 128 * r, 0, BAR(B_XFULL + kb));
                }
            }
            PROFH(0);
#pragma unroll 1
            for (int mt = 0; mt < 4; mt++) {
                if (mt == 1) {
                    if (!early && gemv) {
#pragma unroll 1
                        for (int k = 0; k < 4; k++) tma3_e(wmbuf + k * 7168, &p.wm, mcol + (k >> 1) * 16, (k & 1) * 224, 0, BAR(B_WMFULL));
                    }
                    bar_sync(9, 384);
                    if (sc) return;
                    mbar_wait(BAR(B_MOD1), 0);
                    mbar_wait(BAR(B_WMFREE), 0);
                }
                if (mt == 2) mbar_wait(BAR(B_XFREE), 0);
                if (mt == 3) mbar_wait(BAR(B_VRFULL), 0);
                const uint32_t bar = BAR(mt == 3 ? B_WOFULL : B_FULLK + mt), dst = sb + (mt < 2 ? OFF_Y : OFF_X) + (mt & 1) * HALF;
                const int c0 = (mt < 2 ? DM + DM * mt : 0) + 56 * j - 8 * kh;
                if (!sc) {
                    expect_e(bar, HALF);
                    tma3_e(dst, mt == 3 ? &p.wo : &p.qkv, c0, 0, 0, bar);
                    tma3_e(dst + HALF / 2, mt == 3 ? &p.wo : &p.qkv, c0, 224, 0, bar);
                }
                if (mt & 1) PROFH(1 + (mt >> 1));
            }
            expect_e(BAR(B_XCH), 14336);
            expect_e(BAR(B_XCH + 1), 14336);
        } else {
            if (warp == 10 && lane == 0 && !sc) {
                const uint32_t ticket = atomicAdd(&g_ticket, 1u);
                l2_prefetch((const char*)p.wqkv + (size_t)b * 9408, 9408);
                sts1(sb + M_EPOCH, ticket / NCTA);
            }
            if (warp == 11) {
#pragma unroll
                for (int i = 0; i < 8; i++) {
                    const int wd = lane + 32 * i;
                    const uint32_t cb = i < 7 ? __ldg((const uint32_t*)p.c + wd) : 0u;
                    sts1(wmbuf + 28672 + (wd >> 3) * 32 + (wd & 3) * 8 + (wd & 4), pack2(silu_bf(cb & 0xFFFFu), silu_bf(cb >> 16)));
                }
            }
            bar_sync(9, 384);
            if (sc) return;
            target = lds1(sb + M_EPOCH) + 1;
            const uint32_t tag = target & 0xFFFFu;
            if (warp == 11) {
                warp_arrive(BAR(B_WMFULL));
                mbar_wait(BAR(B_GEMV), 0);
                float sum = 0.f;
#pragma unroll
                for (int i = 0; i < 8; i++) sum += *(const float*)(smem + OFF_Y + HALF + 29696 + (i * 32 + (early ? lane & 15 : lane)) * 4);
                const uint32_t word = (pack2(sum, 0.f) << 16) | tag;
                if (gemv) {
                    uint32_t* mg = g_mod + mcol + (early ? (lane & 15) + (lane >> 4) * 4 * 6 * DM : lane);
#pragma unroll
                    for (int i = 0; i < 8; i++) if (i < 4 || !early) st_relaxed(mg + i * 6 * DM, word);
                }
                warp_arrive(BAR(B_WMFREE));
                PROFH(5);
            }
            const uint4* modp = (const uint4*)g_mod + (r & 7) * (6 * DM / 4);
            const bool p2 = warp == 11;
            mbar_wait(BAR(p2 ? B_PUB : B_XFULL + 4), 0);
#pragma unroll 1
            for (int it = p2 ? 0 : warp - 9; it < (p2 ? 2 : warp - 8); it++) {
                const int i0 = lane + 32 * it, imax = p2 ? 251 : 223;
                uint4 v[4];
#pragma unroll 1
                for (int n = 0;; n++) {
                    uint32_t bad = 0;
#pragma unroll
                    for (int k = 0; k < 4; k++) {
                        const int i = min(i0 + 64 * k, imax);
                        v[k] = ld_relaxed4(modp + (i < 224 ? (p2 ? 336 : 0) + i : (i < 238 ? 14 * j + i : 14 * j + i + 322)));
                        bad |= (v[k].x ^ tag) | (v[k].y ^ tag) | (v[k].z ^ tag) | (v[k].w ^ tag);
                    }
                    if (!(bad & 0xFFFFu)) break;
                    if (n > SPIN_LIMIT) __trap();
                }
#pragma unroll
                for (int k = 0; k < 4; k++) {
                    const int i = min(i0 + 64 * k, imax);
                    if (i < 224) {
                        const int isc = i >= 112, c4 = i - 112 * isc;
                        const float one = isc ? 1.f : 0.f;
                        const uint32_t a = sb + M_ST + (c4 >> 2) * 64 + (c4 & 1) * 32 + (c4 & 2) * 4 + (isc ? 0 : 4);
                        sts1(a, pack2(bf_hi(v[k].x) + one, bf_hi(v[k].y) + one));
                        sts1(a + 16, pack2(bf_hi(v[k].z) + one, bf_hi(v[k].w) + one));
                    } else {
                        sts4(sb + M_G + (i - 224) * 16, make_uint4(v[k].x & 0xFFFF0000u, v[k].y & 0xFFFF0000u, v[k].z & 0xFFFF0000u, v[k].w & 0xFFFF0000u));
                    }
                }
                warp_arrive(BAR(p2 ? B_MOD2 : B_MOD1));
            }
            if (warp == 9) PROFH(6);
            if (warp == 9) {
#pragma unroll 1
                for (int kv = 0; kv < 2; kv++) {
                    mbar_wait(BAR(B_PUB + kv), 0);
                    if (lane >= 1 && lane <= 2 && r >= lane) wait_flag(g_flag + kv * 128 + b - 8 * lane, target);
                    __syncwarp();
                    fence_async_global();
                    const uint32_t dst = sb + OFF_Y + (kv ? Y_VR : Y_K);
                    expect_e(BAR(B_KRFULL + kv), r >= 2 ? 28672 : r == 1 ? 14336 : 0);
                    if (r >= 2) bulk_e(dst, g_kv + (size_t)((b - 16) * 2 + kv) * 3584, 14336, BAR(B_KRFULL + kv));
                    if (r >= 1) bulk_e(dst + 14336, g_kv + (size_t)((b - 8) * 2 + kv) * 3584, 14336, BAR(B_KRFULL + kv));
                    PROFH(7 + kv);
                }
            } else if (warp == 11) {
                mbar_wait(BAR(B_VRFULL), 0);
                if (lane == 0) {
                    l2_prefetch((const char*)p.wg + (size_t)b * 12544, 12544);
                    l2_prefetch((const char*)p.wu + (size_t)b * 12544, 12544);
                    l2_prefetch((const char*)p.wd + (size_t)b * 12544, 12544);
                }
                __syncwarp();
            }
        }
        if (warp == 8 || warp == 11) {
            const int sec = warp == 11;
            int sl = 0;
#pragma unroll 1
            for (int s = 0; s < 28; s++) {
                if (s >= 1 && s < 6) mbar_wait(BAR(B_FULL + s - 1), 0);
                const bool pa = s < 14;
                const uint32_t half = pa ? 8192 : 6144;
                mbar_wait(BAR(B_EMPTY + sl), (s >= 7 && s < 14) || s >= 21);
                expect_e(BAR(B_FULL + sl), half);
                tma3_e(sb + slot_off(sl) + sec * half, &p.ga + (pa ? 0 : 2) + sec, 0, 32 * (pa ? s : s - 14), pa ? fa >> 6 : fb >> 5, BAR(B_FULL + sl));
                sl = sl == 6 ? 0 : sl + 1;
            }
            if (!sec) PROFH(3);
            sl = 0;
            int u = 0;
#pragma unroll 1
            for (int grp = 0; grp < 8; grp++) {
                const bool pa = grp < 4, own = grp == 3 || grp == 4;
                int sidx = pa ? grp : grp - 5;
                sidx = own ? nq : sidx + (sidx >= nq);
                const int ofs = 4 * kh + sidx;
                int f = 224 * ofs + ((ofs & 1) ? (pa ? 96 : 0) : (pa ? 0 : 128));
                if (sec && (grp == 0 || grp == 5)) { mbar_wait(BAR(B_HRDY + !pa), 0); fence_async_global(); }
#pragma unroll 1
                for (int k = pa ? 0 : 1; k < 4; k++, u++, f += 32) {
                    const uint32_t dst = sb + slot_off(sl), bar = BAR(B_FULL + sl);
                    mbar_wait(BAR(B_EMPTY + sl), u >= 12 && u < 24);
                    if (!sec) {
                        expect_e(bar, 8192);
                        tma3_e(dst, &p.dn, 0, nq, f, bar);
                        tma3_e(dst + 4096, &p.dn, 64, nq, f, bar);
                    } else {
                        expect_e(bar, own ? 0 : 8192);
                        if (!own) bulk_e(dst + 8192, g_h2 + (size_t)r * (224 * 512) + f * 64, 8192, bar);
                    }
                    sl = sl == 11 ? 0 : sl + 1;
                }
            }
            if (!sec) PROFH(4);
            mbar_wait(BAR(B_DONE), 0);
        } else if (warp == 9) {
#pragma unroll
            for (int ev = 0; ev < 4; ev++) expect_e(BAR(B_GFULL + ev), ev < 2 ? HALF : HALF + 4096);
            mbar_wait(BAR(B_PUB + 2), 0);
            uint32_t todo = ~0u;
#pragma unroll 1
            for (int n = 0; todo; n++) {
                if (todo == 0xFFFFFF00u) mbar_wait(BAR(B_PUB + 3), 0);
                uint32_t ok = __ballot_sync(~0u, (int)(ld_acquire(g_flag + (2 + (lane >> 3)) * 128 + 8 * r + (lane & 7)) - target) >= 0);
                uint32_t en = (ok >> j) & 0x01010101u;
                en &= (en << 8) | 0x0101u;
                en &= (en << 8) | 0x010101u;
                ok &= (en * 0xFFu) & todo;
                todo &= ~ok;
                fence_async_global();
#pragma unroll 1
                while (ok) {
                    const int bit = __ffs(ok) - 1, ev = bit >> 3, jj = bit & 7, len = min(__ffs(~(ok >> bit) | 256u) - 1, 8 - jj);
                    ok &= ~(((1u << len) - 1u) << bit);
                    const uint32_t bar = BAR(B_GFULL + ev);
                    const int sl = (2 * r + (ev & 1)) * 8 + jj;
                    bulk_e(sb + (ev == 0 ? OFF_X : OFF_Y + (ev & 1) * HALF) + jj * 7168, g_ox + (ev >> 1) * (34 * 14336) + sl * 1792, len * 7168, bar);
                    if (ev >= 2) bulk_e(sb + OFF_X + X_STAT + (bit & 15) * 512, g_st + sl * 64, len * 512, bar);
                }
                if (n > SPIN_LIMIT) __trap();
            }
#pragma unroll 1
            for (int ps = 0; ps < 2; ps++) {
                mbar_wait(BAR(B_PUB + 6 + ps), 0);
                if (lane < 4) wait_flag(g_flag + (6 + ps) * 128 + 8 * r + 2 * lane + kh, target);
                warp_arrive(BAR(B_HRDY + ps));
                PROFH(10 + ps);
            }
        } else {
            if (lane == 0) {
#pragma unroll 1
                for (int k = 0; k < 8; k++) {
                    mbar_wait(BAR(B_PUB + k), 0);
                    fence_gpu();
                    st_relaxed(g_flag + k * 128 + b, target);
                    if (k == 5) PROFH1(9);
                }
            }
        }
    }
}

typedef CUresult (*EncodeFn)(CUtensorMap*, CUtensorMapDataType, cuuint32_t, void*, const cuuint64_t*, const cuuint64_t*, const cuuint32_t*,
                             const cuuint32_t*, CUtensorMapInterleave, CUtensorMapSwizzle, CUtensorMapL2promotion, CUtensorMapFloatOOBfill);

static void make_map(EncodeFn fn, CUtensorMap* m, const void* ptr, uint64_t d0, uint64_t d1, uint64_t d2, uint64_t s1, uint64_t s2,
                     uint32_t b0, uint32_t b1, uint32_t b2, CUtensorMapSwizzle sw) {
    cuuint64_t dims[3] = {d0, d1, d2}, strides[2] = {s1, s2};
    cuuint32_t box[3] = {b0, b1, b2}, es[3] = {1, 1, 1};
    CUresult rc = fn(m, CU_TENSOR_MAP_DATA_TYPE_BFLOAT16, 3, (void*)ptr, dims, strides, box, es, CU_TENSOR_MAP_INTERLEAVE_NONE, sw,
                     CU_TENSOR_MAP_L2_PROMOTION_L2_128B, CU_TENSOR_MAP_FLOAT_OOB_FILL_NONE);
    (void)rc;
}

extern "C" void kernel_launch(void* const* d_in, const int* in_sizes, int n_in, void* d_out, int out_size) {
    (void)in_sizes; (void)n_in; (void)out_size;
    static EncodeFn fn = nullptr;
    if (!fn) {
        cudaDriverEntryPointQueryResult st;
        cudaGetDriverEntryPoint("cuTensorMapEncodeTiled", (void**)&fn, cudaEnableDefault, &st);
        cudaFuncSetAttribute(fused_block_kernel, cudaFuncAttributeMaxDynamicSharedMemorySize, SMEM_BYTES);
    }
    Params p;
    p.x = (const bf16*)d_in[0];
    const bf16* wqkv = (const bf16*)d_in[1];
    p.wqkv = wqkv;
    p.wop = (const bf16*)d_in[2];
    p.wg = (const bf16*)d_in[4];
    p.wu = (const bf16*)d_in[5];
    p.wd = (const bf16*)d_in[6];
    p.c = (const bf16*)d_in[7];
    p.wmod = (const bf16*)d_in[8];
    p.out = (bf16*)d_out;
    p.zero = 0;
    make_map(fn, &p.wm, p.wmod, 2688, 448, 1, 5376, 5376 * 448, 16, 224, 1, CU_TENSOR_MAP_SWIZZLE_NONE);
    make_map(fn, &p.xm, p.x, 448, 2048, 1, 896, 896 * 2048, 64, 128, 1, CU_TENSOR_MAP_SWIZZLE_128B);
    make_map(fn, &p.qkv, wqkv, 1344, 448, 1, 2688, 2688 * 448, 64, 224, 1, CU_TENSOR_MAP_SWIZZLE_128B);
    make_map(fn, &p.wo, p.wop, 448, 448, 1, 896, 896 * 448, 64, 224, 1, CU_TENSOR_MAP_SWIZZLE_128B);
    make_map(fn, &p.ga, p.wg, 64, 448, 28, 3584, 128, 64, 32, 2, CU_TENSOR_MAP_SWIZZLE_128B);
    make_map(fn, &p.ua, p.wu, 64, 448, 28, 3584, 128, 64, 32, 2, CU_TENSOR_MAP_SWIZZLE_128B);
    make_map(fn, &p.gb, p.wg, 32, 448, 56, 3584, 64, 32, 32, 3, CU_TENSOR_MAP_SWIZZLE_64B);
    make_map(fn, &p.ub, p.wu, 32, 448, 56, 3584, 64, 32, 32, 3, CU_TENSOR_MAP_SWIZZLE_64B);
    make_map(fn, &p.dn, p.wd, 112, 4, 1792, 224, 896, 64, 1, 32, CU_TENSOR_MAP_SWIZZLE_128B);
    fused_block_kernel<<<GRID, 384, SMEM_BYTES>>>(p);
}
```

```cpp
#include <cuda_runtime.h>
#include <cuda_bf16.h>
#include <cuda.h>
#include <stdint.h>

typedef __nv_bfloat16 bf16;

template<int TB> __device__ __forceinline__ void wgmma_rs_56(float* d, uint32_t a0, uint32_t a1, uint32_t a2, uint32_t a3, uint64_t db, int sd) {
  asm volatile("{\n.reg .pred p;\nsetp.ne.b32 p, %33, 0;\n"
    "wgmma.mma_async.sync.aligned.m64n56k16.f32.bf16.bf16 {%0,%1,%2,%3,%4,%5,%6,%7,%8,%9,%10,%11,%12,%13,%14,%15,%16,%17,%18,%19,%20,%21,%22,%23,%24,%25,%26,%27}, {%28,%29,%30,%31}, %32, p, 1, 1, %34;\n}\n"
    : "+f"(d[0]),"+f"(d[1]),"+f"(d[2]),"+f"(d[3]),"+f"(d[4]),"+f"(d[5]),"+f"(d[6]),"+f"(d[7]),"+f"(d[8]),"+f"(d[9]),"+f"(d[10]),"+f"(d[11]),"+f"(d[12]),"+f"(d[13]),"+f"(d[14]),"+f"(d[15]),"+f"(d[16]),"+f"(d[17]),"+f"(d[18]),"+f"(d[19]),"+f"(d[20]),"+f"(d[21]),"+f"(d[22]),"+f"(d[23]),"+f"(d[24]),"+f"(d[25]),"+f"(d[26]),"+f"(d[27])
    : "r"(a0), "r"(a1), "r"(a2), "r"(a3), "l"(db), "r"(sd), "n"(TB));
}
template<int TB> __device__ __forceinline__ void wgmma_ss_56(float* d, uint64_t da, uint64_t db, int sd) {
  asm volatile("{\n.reg .pred p;\nsetp.ne.b32 p, %30, 0;\n"
    "wgmma.mma_async.sync.aligned.m64n56k16.f32.bf16.bf16 {%0,%1,%2,%3,%4,%5,%6,%7,%8,%9,%10,%11,%12,%13,%14,%15,%16,%17,%18,%19,%20,%21,%22,%23,%24,%25,%26,%27}, %28, %29, p, 1, 1, 0, %31;\n}\n"
    : "+f"(d[0]),"+f"(d[1]),"+f"(d[2]),"+f"(d[3]),"+f"(d[4]),"+f"(d[5]),"+f"(d[6]),"+f"(d[7]),"+f"(d[8]),"+f"(d[9]),"+f"(d[10]),"+f"(d[11]),"+f"(d[12]),"+f"(d[13]),"+f"(d[14]),"+f"(d[15]),"+f"(d[16]),"+f"(d[17]),"+f"(d[18]),"+f"(d[19]),"+f"(d[20]),"+f"(d[21]),"+f"(d[22]),"+f"(d[23]),"+f"(d[24]),"+f"(d[25]),"+f"(d[26]),"+f"(d[27])
    : "l"(da), "l"(db), "r"(sd), "n"(TB));
}
template<int TB> __device__ __forceinline__ void wgmma_rs_256(float* d, uint32_t a0, uint32_t a1, uint32_t a2, uint32_t a3, uint64_t db, int sd) {
  asm volatile("{\n.reg .pred p;\nsetp.ne.b32 p, %133, 0;\n"
    "wgmma.mma_async.sync.aligned.m64n256k16.f32.bf16.bf16 {%0,%1,%2,%3,%4,%5,%6,%7,%8,%9,%10,%11,%12,%13,%14,%15,%16,%17,%18,%19,%20,%21,%22,%23,%24,%25,%26,%27,%28,%29,%30,%31,%32,%33,%34,%35,%36,%37,%38,%39,%40,%41,%42,%43,%44,%45,%46,%47,%48,%49,%50,%51,%52,%53,%54,%55,%56,%57,%58,%59,%60,%61,%62,%63,%64,%65,%66,%67,%68,%69,%70,%71,%72,%73,%74,%75,%76,%77,%78,%79,%80,%81,%82,%83,%84,%85,%86,%87,%88,%89,%90,%91,%92,%93,%94,%95,%96,%97,%98,%99,%100,%101,%102,%103,%104,%105,%106,%107,%108,%109,%110,%111,%112,%113,%114,%115,%116,%117,%118,%119,%120,%121,%122,%123,%124,%125,%126,%127}, {%128,%129,%130,%131}, %132, p, 1, 1, %134;\n}\n"
    : "+f"(d[0]),"+f"(d[1]),"+f"(d[2]),"+f"(d[3]),"+f"(d[4]),"+f"(d[5]),"+f"(d[6]),"+f"(d[7]),"+f"(d[8]),"+f"(d[9]),"+f"(d[10]),"+f"(d[11]),"+f"(d[12]),"+f"(d[13]),"+f"(d[14]),"+f"(d[15]),"+f"(d[16]),"+f"(d[17]),"+f"(d[18]),"+f"(d[19]),"+f"(d[20]),"+f"(d[21]),"+f"(d[22]),"+f"(d[23]),"+f"(d[24]),"+f"(d[25]),"+f"(d[26]),"+f"(d[27]),"+f"(d[28]),"+f"(d[29]),"+f"(d[30]),"+f"(d[31]),"+f"(d[32]),"+f"(d[33]),"+f"(d[34]),"+f"(d[35]),"+f"(d[36]),"+f"(d[37]),"+f"(d[38]),"+f"(d[39]),"+f"(d[40]),"+f"(d[41]),"+f"(d[42]),"+f"(d[43]),"+f"(d[44]),"+f"(d[45]),"+f"(d[46]),"+f"(d[47]),"+f"(d[48]),"+f"(d[49]),"+f"(d[50]),"+f"(d[51]),"+f"(d[52]),"+f"(d[53]),"+f"(d[54]),"+f"(d[55]),"+f"(d[56]),"+f"(d[57]),"+f"(d[58]),"+f"(d[59]),"+f"(d[60]),"+f"(d[61]),"+f"(d[62]),"+f"(d[63]),"+f"(d[64]),"+f"(d[65]),"+f"(d[66]),"+f"(d[67]),"+f"(d[68]),"+f"(d[69]),"+f"(d[70]),"+f"(d[71]),"+f"(d[72]),"+f"(d[73]),"+f"(d[74]),"+f"(d[75]),"+f"(d[76]),"+f"(d[77]),"+f"(d[78]),"+f"(d[79]),"+f"(d[80]),"+f"(d[81]),"+f"(d[82]),"+f"(d[83]),"+f"(d[84]),"+f"(d[85]),"+f"(d[86]),"+f"(d[87]),"+f"(d[88]),"+f"(d[89]),"+f"(d[90]),"+f"(d[91]),"+f"(d[92]),"+f"(d[93]),"+f"(d[94]),"+f"(d[95]),"+f"(d[96]),"+f"(d[97]),"+f"(d[98]),"+f"(d[99]),"+f"(d[100]),"+f"(d[101]),"+f"(d[102]),"+f"(d[103]),"+f"(d[104]),"+f"(d[105]),"+f"(d[106]),"+f"(d[107]),"+f"(d[108]),"+f"(d[109]),"+f"(d[110]),"+f"(d[111]),"+f"(d[112]),"+f"(d[113]),"+f"(d[114]),"+f"(d[115]),"+f"(d[116]),"+f"(d[117]),"+f"(d[118]),"+f"(d[119]),"+f"(d[120]),"+f"(d[121]),"+f"(d[122]),"+f"(d[123]),"+f"(d[124]),"+f"(d[125]),"+f"(d[126]),"+f"(d[127])
    : "r"(a0), "r"(a1), "r"(a2), "r"(a3), "l"(db), "r"(sd), "n"(TB));
}
template<int TB> __device__ __forceinline__ void wgmma_ss_192(float* d, uint64_t da, uint64_t db, int sd) {
  asm volatile("{\n.reg .pred p;\nsetp.ne.b32 p, %98, 0;\n"
    "wgmma.mma_async.sync.aligned.m64n192k16.f32.bf16.bf16 {%0,%1,%2,%3,%4,%5,%6,%7,%8,%9,%10,%11,%12,%13,%14,%15,%16,%17,%18,%19,%20,%21,%22,%23,%24,%25,%26,%27,%28,%29,%30,%31,%32,%33,%34,%35,%36,%37,%38,%39,%40,%41,%42,%43,%44,%45,%46,%47,%48,%49,%50,%51,%52,%53,%54,%55,%56,%57,%58,%59,%60,%61,%62,%63,%64,%65,%66,%67,%68,%69,%70,%71,%72,%73,%74,%75,%76,%77,%78,%79,%80,%81,%82,%83,%84,%85,%86,%87,%88,%89,%90,%91,%92,%93,%94,%95}, %96, %97, p, 1, 1, 0, %99;\n}\n"
    : "+f"(d[0]),"+f"(d[1]),"+f"(d[2]),"+f"(d[3]),"+f"(d[4]),"+f"(d[5]),"+f"(d[6]),"+f"(d[7]),"+f"(d[8]),"+f"(d[9]),"+f"(d[10]),"+f"(d[11]),"+f"(d[12]),"+f"(d[13]),"+f"(d[14]),"+f"(d[15]),"+f"(d[16]),"+f"(d[17]),"+f"(d[18]),"+f"(d[19]),"+f"(d[20]),"+f"(d[21]),"+f"(d[22]),"+f"(d[23]),"+f"(d[24]),"+f"(d[25]),"+f"(d[26]),"+f"(d[27]),"+f"(d[28]),"+f"(d[29]),"+f"(d[30]),"+f"(d[31]),"+f"(d[32]),"+f"(d[33]),"+f"(d[34]),"+f"(d[35]),"+f"(d[36]),"+f"(d[37]),"+f"(d[38]),"+f"(d[39]),"+f"(d[40]),"+f"(d[41]),"+f"(d[42]),"+f"(d[43]),"+f"(d[44]),"+f"(d[45]),"+f"(d[46]),"+f"(d[47]),"+f"(d[48]),"+f"(d[49]),"+f"(d[50]),"+f"(d[51]),"+f"(d[52]),"+f"(d[53]),"+f"(d[54]),"+f"(d[55]),"+f"(d[56]),"+f"(d[57]),"+f"(d[58]),"+f"(d[59]),"+f"(d[60]),"+f"(d[61]),"+f"(d[62]),"+f"(d[63]),"+f"(d[64]),"+f"(d[65]),"+f"(d[66]),"+f"(d[67]),"+f"(d[68]),"+f"(d[69]),"+f"(d[70]),"+f"(d[71]),"+f"(d[72]),"+f"(d[73]),"+f"(d[74]),"+f"(d[75]),"+f"(d[76]),"+f"(d[77]),"+f"(d[78]),"+f"(d[79]),"+f"(d[80]),"+f"(d[81]),"+f"(d[82]),"+f"(d[83]),"+f"(d[84]),"+f"(d[85]),"+f"(d[86]),"+f"(d[87]),"+f"(d[88]),"+f"(d[89]),"+f"(d[90]),"+f"(d[91]),"+f"(d[92]),"+f"(d[93]),"+f"(d[94]),"+f"(d[95])
    : "l"(da), "l"(db), "r"(sd), "n"(TB));
}
template<int TB> __device__ __forceinline__ void wgmma_ss_112(float* d, uint64_t da, uint64_t db, int sd) {
  asm volatile("{\n.reg .pred p;\nsetp.ne.b32 p, %58, 0;\n"
    "wgmma.mma_async.sync.aligned.m64n112k16.f32.bf16.bf16 {%0,%1,%2,%3,%4,%5,%6,%7,%8,%9,%10,%11,%12,%13,%14,%15,%16,%17,%18,%19,%20,%21,%22,%23,%24,%25,%26,%27,%28,%29,%30,%31,%32,%33,%34,%35,%36,%37,%38,%39,%40,%41,%42,%43,%44,%45,%46,%47,%48,%49,%50,%51,%52,%53,%54,%55}, %56, %57, p, 1, 1, 0, %59;\n}\n"
    : "+f"(d[0]),"+f"(d[1]),"+f"(d[2]),"+f"(d[3]),"+f"(d[4]),"+f"(d[5]),"+f"(d[6]),"+f"(d[7]),"+f"(d[8]),"+f"(d[9]),"+f"(d[10]),"+f"(d[11]),"+f"(d[12]),"+f"(d[13]),"+f"(d[14]),"+f"(d[15]),"+f"(d[16]),"+f"(d[17]),"+f"(d[18]),"+f"(d[19]),"+f"(d[20]),"+f"(d[21]),"+f"(d[22]),"+f"(d[23]),"+f"(d[24]),"+f"(d[25]),"+f"(d[26]),"+f"(d[27]),"+f"(d[28]),"+f"(d[29]),"+f"(d[30]),"+f"(d[31]),"+f"(d[32]),"+f"(d[33]),"+f"(d[34]),"+f"(d[35]),"+f"(d[36]),"+f"(d[37]),"+f"(d[38]),"+f"(d[39]),"+f"(d[40]),"+f"(d[41]),"+f"(d[42]),"+f"(d[43]),"+f"(d[44]),"+f"(d[45]),"+f"(d[46]),"+f"(d[47]),"+f"(d[48]),"+f"(d[49]),"+f"(d[50]),"+f"(d[51]),"+f"(d[52]),"+f"(d[53]),"+f"(d[54]),"+f"(d[55])
    : "l"(da), "l"(db), "r"(sd), "n"(TB));
}
template<int TB> __device__ __forceinline__ void wgmma_rs_112(float* d, uint32_t a0, uint32_t a1, uint32_t a2, uint32_t a3, uint64_t db, int sd) {
  asm volatile("{\n.reg .pred p;\nsetp.ne.b32 p, %61, 0;\n"
    "wgmma.mma_async.sync.aligned.m64n112k16.f32.bf16.bf16 {%0,%1,%2,%3,%4,%5,%6,%7,%8,%9,%10,%11,%12,%13,%14,%15,%16,%17,%18,%19,%20,%21,%22,%23,%24,%25,%26,%27,%28,%29,%30,%31,%32,%33,%34,%35,%36,%37,%38,%39,%40,%41,%42,%43,%44,%45,%46,%47,%48,%49,%50,%51,%52,%53,%54,%55}, {%56,%57,%58,%59}, %60, p, 1, 1, %62;\n}\n"
    : "+f"(d[0]),"+f"(d[1]),"+f"(d[2]),"+f"(d[3]),"+f"(d[4]),"+f"(d[5]),"+f"(d[6]),"+f"(d[7]),"+f"(d[8]),"+f"(d[9]),"+f"(d[10]),"+f"(d[11]),"+f"(d[12]),"+f"(d[13]),"+f"(d[14]),"+f"(d[15]),"+f"(d[16]),"+f"(d[17]),"+f"(d[18]),"+f"(d[19]),"+f"(d[20]),"+f"(d[21]),"+f"(d[22]),"+f"(d[23]),"+f"(d[24]),"+f"(d[25]),"+f"(d[26]),"+f"(d[27]),"+f"(d[28]),"+f"(d[29]),"+f"(d[30]),"+f"(d[31]),"+f"(d[32]),"+f"(d[33]),"+f"(d[34]),"+f"(d[35]),"+f"(d[36]),"+f"(d[37]),"+f"(d[38]),"+f"(d[39]),"+f"(d[40]),"+f"(d[41]),"+f"(d[42]),"+f"(d[43]),"+f"(d[44]),"+f"(d[45]),"+f"(d[46]),"+f"(d[47]),"+f"(d[48]),"+f"(d[49]),"+f"(d[50]),"+f"(d[51]),"+f"(d[52]),"+f"(d[53]),"+f"(d[54]),"+f"(d[55])
    : "r"(a0), "r"(a1), "r"(a2), "r"(a3), "l"(db), "r"(sd), "n"(TB));
}

constexpr int DM = 448;
constexpr int NCTA = 128;
#define MAPPING 1
#define GRID 132
#define PINGPONG 0
#define NPOLL 4
#define POLL_GAP 150
#define ALLATONCE 0
#define MAP_S 4
constexpr int SPIN_LIMIT = 1 << 22;

constexpr uint32_t OFF_X = 0, OFF_Y = 114688, OFF_MISC = 229376, SMEM_BYTES = 232448;
constexpr uint32_t Y_VR = 0, Y_K = 28672, Y_KOWN = 57344, Y_VOWN = 71680, Y_Q = 86016;
constexpr uint32_t HALF = 57344;
constexpr uint32_t M_BAR = OFF_MISC;
constexpr uint32_t M_ST = OFF_MISC + 512;
constexpr uint32_t M_G = OFF_MISC + 2304;
constexpr uint32_t M_EPOCH = OFF_MISC + 3040;
enum { B_XFULL = 0, B_FULLK = 7, B_FULLV = 8, B_FULLQ, B_KRFULL, B_VRFULL, B_WOFULL, B_XCH, B_FULL = 16, B_MOD1 = 28, B_MOD2, B_WMFULL,
       B_EMPTY = 32, B_XFREE = B_EMPTY + 12, B_GEMV, B_PEER, B_DONE,
       B_PUB = 48,
       B_WMFREE = 56, B_HRDY, B_GFULL = B_HRDY + 2 };
constexpr uint32_t X_STAT = 49152;

__device__ uint32_t g_ticket;
__device__ __align__(128) uint32_t g_mod[8 * 6 * DM];
__device__ __align__(128) uint32_t g_flag[8 * 16 * 8];
__device__ __align__(128) uint32_t g_kv[17 * 8 * 2 * 3584];
__device__ __align__(128) uint32_t g_ox[2 * 34 * 14336];
#define g_o g_ox
#define g_x1 (g_ox + 34 * 14336)
__device__ __align__(128) float2 g_st[34 * 8 * 64];
__device__ __align__(128) uint32_t g_h2[17 * 224 * 512];
#define PROFH(id)
#define PROFH1(id)
#define PROFC(id)

struct alignas(64) Params {
    CUtensorMap wm, xm, qkv, wo, ga, ua, gb, ub, dn;
    const bf16 *x, *c, *wqkv, *wmod, *wg, *wu, *wd, *wop;
    bf16* out;
    uint32_t zero;
};

__device__ __forceinline__ void mbar_init(uint32_t bar, int cnt) { asm volatile("mbarrier.init.shared::cta.b64 [%0], %1;" ::"r"(bar), "r"(cnt) : "memory"); }
__device__ __forceinline__ void mbar_expect_tx(uint32_t bar, uint32_t bytes) { asm volatile("mbarrier.arrive.expect_tx.shared::cta.b64 _, [%0], %1;" ::"r"(bar), "r"(bytes) : "memory"); }
__device__ __forceinline__ void mbar_arrive(uint32_t bar) { asm volatile("mbarrier.arrive.shared::cta.b64 _, [%0];" ::"r"(bar) : "memory"); }
__device__ __forceinline__ void mbar_wait(uint32_t bar, uint32_t parity) {
    uint32_t ok; int n = 0;
    do {
        asm volatile("{\n.reg .pred p;\nmbarrier.try_wait.parity.shared::cta.b64 p, [%1], %2;\nselp.u32 %0, 1, 0, p;\n}" : "=r"(ok) : "r"(bar), "r"(parity) : "memory");
        if (++n > SPIN_LIMIT) __trap();
    } while (!ok);
}
__device__ __forceinline__ void mbar_wait_cluster(uint32_t bar, uint32_t parity) {
    uint32_t ok; int n = 0;
    do {
        asm volatile("{\n.reg .pred p;\nmbarrier.try_wait.parity.acquire.cluster.shared::cta.b64 p, [%1], %2;\nselp.u32 %0, 1, 0, p;\n}" : "=r"(ok) : "r"(bar), "r"(parity) : "memory");
        if (++n > SPIN_LIMIT) __trap();
    } while (!ok);
}
__device__ __forceinline__ void warp_arrive(uint32_t bar) {
    __syncwarp();
    asm volatile("{\n.reg .pred p;\nelect.sync _|p, 0xffffffff;\n@p mbarrier.arrive.shared::cta.b64 _, [%0];\n}" ::"r"(bar) : "memory");
}
__device__ __forceinline__ int opaque(int v) { return __shfl_sync(~0u, v, 0); }
__device__ __forceinline__ int fresh_tid() { int v; asm volatile("mov.u32 %0, %%tid.x;" : "=r"(v)); return v; }
__device__ __forceinline__ void bar_sync(int id, int n) { asm volatile("bar.sync %0, %1;" ::"r"(id), "r"(n) : "memory"); }
__device__ __forceinline__ void bar_arrive(int id, int n) { asm volatile("bar.arrive %0, %1;" ::"r"(id), "r"(n) : "memory"); }
__device__ __forceinline__ void fence_async_smem() { asm volatile("fence.proxy.async.shared::cta;" ::: "memory"); }
__device__ __forceinline__ void fence_async_global() { asm volatile("fence.proxy.async.global;" ::: "memory"); }
__device__ __forceinline__ void fence_gpu() { asm volatile("fence.release.gpu;" ::: "memory"); }
__device__ __forceinline__ void tma3(uint32_t dst, const CUtensorMap* m, int c0, int c1, int c2, uint32_t bar) {
    asm volatile("cp.async.bulk.tensor.3d.shared::cluster.global.mbarrier::complete_tx::bytes [%0], [%1, {%3, %4, %5}], [%2];"
                 ::"r"(dst), "l"(m), "r"(bar), "r"(c0), "r"(c1), "r"(c2) : "memory");
}
__device__ __forceinline__ void bulk_load(uint32_t dst, const void* src, uint32_t bytes, uint32_t bar) {
    asm volatile("cp.async.bulk.shared::cluster.global.mbarrier::complete_tx::bytes [%0], [%1], %2, [%3];" ::"r"(dst), "l"(src), "r"(bytes), "r"(bar) : "memory");
}
__device__ __forceinline__ void expect_e(uint32_t bar, uint32_t bytes) {
    asm volatile("{\n.reg .pred p;\nelect.sync _|p, 0xffffffff;\n@p mbarrier.arrive.expect_tx.shared::cta.b64 _, [%0], %1;\n}" ::"r"(bar), "r"(bytes) : "memory");
}
__device__ __forceinline__ void tma3_e(uint32_t dst, const CUtensorMap* m, int c0, int c1, int c2, uint32_t bar) {
    asm volatile("{\n.reg .pred p;\nelect.sync _|p, 0xffffffff;\n@p cp.async.bulk.tensor.3d.shared::cluster.global.mbarrier::complete_tx::bytes [%0], [%1, {%3, %4, %5}], [%2];\n}"
                 ::"r"(dst), "l"(m), "r"(bar), "r"(c0), "r"(c1), "r"(c2) : "memory");
}
__device__ __forceinline__ void bulk_e(uint32_t dst, const void* src, uint32_t bytes, uint32_t bar) {
    asm volatile("{\n.reg .pred p;\nelect.sync _|p, 0xffffffff;\n@p cp.async.bulk.shared::cluster.global.mbarrier::complete_tx::bytes [%0], [%1], %2, [%3];\n}"
                 ::"r"(dst), "l"(src), "r"(bytes), "r"(bar) : "memory");
}
__device__ __forceinline__ void init_e(uint32_t bar, int cnt) {
    asm volatile("{\n.reg .pred p;\nelect.sync _|p, 0xffffffff;\n@p mbarrier.init.shared::cta.b64 [%0], %1;\n}" ::"r"(bar), "r"(cnt) : "memory");
}
__device__ __forceinline__ void l2_prefetch(const void* src, uint32_t bytes) { asm volatile("cp.async.bulk.prefetch.L2.global [%0], %1;" ::"l"(src), "r"(bytes) : "memory"); }
__device__ __forceinline__ uint32_t ld_relaxed(const uint32_t* p) { uint32_t v; asm volatile("ld.relaxed.gpu.global.u32 %0, [%1];" : "=r"(v) : "l"(p) : "memory"); return v; }
__device__ __forceinline__ void st_relaxed(uint32_t* p, uint32_t v) { asm volatile("st.relaxed.gpu.global.u32 [%0], %1;" ::"l"(p), "r"(v) : "memory"); }
__device__ __forceinline__ uint4 ld_relaxed4(const uint4* p) { uint4 v; asm volatile("ld.relaxed.gpu.global.v4.u32 {%0,%1,%2,%3}, [%4];" : "=r"(v.x), "=r"(v.y), "=r"(v.z), "=r"(v.w) : "l"(p) : "memory"); return v; }
__device__ __forceinline__ void st_relaxed4(uint4* p, uint4 v) { asm volatile("st.relaxed.gpu.global.v4.u32 [%0], {%1,%2,%3,%4};" ::"l"(p), "r"(v.x), "r"(v.y), "r"(v.z), "r"(v.w) : "memory"); }
__device__ __forceinline__ uint4 ldg_nc4(const void* p) { uint4 v; asm volatile("ld.global.nc.L1::no_allocate.v4.u32 {%0,%1,%2,%3}, [%4];" : "=r"(v.x), "=r"(v.y), "=r"(v.z), "=r"(v.w) : "l"(p)); return v; }
__device__ __forceinline__ uint32_t ldg_nc(const void* p) { uint32_t v; asm volatile("ld.global.nc.u32 %0, [%1];" : "=r"(v) : "l"(p)); return v; }
__device__ __forceinline__ uint32_t ld_acquire(const uint32_t* p) { uint32_t v; asm volatile("ld.acquire.gpu.global.u32 %0, [%1];" : "=r"(v) : "l"(p) : "memory"); return v; }
__device__ __forceinline__ uint4 lds4(uint32_t a) { uint4 v; asm volatile("ld.shared.v4.u32 {%0,%1,%2,%3}, [%4];" : "=r"(v.x), "=r"(v.y), "=r"(v.z), "=r"(v.w) : "r"(a) : "memory"); return v; }
__device__ __forceinline__ float2 lds2f(uint32_t a) { float2 v; asm volatile("ld.shared.v2.f32 {%0,%1}, [%2];" : "=f"(v.x), "=f"(v.y) : "r"(a) : "memory"); return v; }
__device__ __forceinline__ uint32_t lds1(uint32_t a) { uint32_t v; asm volatile("ld.shared.u32 %0, [%1];" : "=r"(v) : "r"(a) : "memory"); return v; }
__device__ __forceinline__ void sts4(uint32_t a, uint4 v) { asm volatile("st.shared.v4.u32 [%0], {%1,%2,%3,%4};" ::"r"(a), "r"(v.x), "r"(v.y), "r"(v.z), "r"(v.w) : "memory"); }
__device__ __forceinline__ void sts2(uint32_t a, uint32_t x, uint32_t y) { asm volatile("st.shared.v2.u32 [%0], {%1,%2};" ::"r"(a), "r"(x), "r"(y) : "memory"); }
__device__ __forceinline__ void sts1(uint32_t a, uint32_t v) { asm volatile("st.shared.u32 [%0], %1;" ::"r"(a), "r"(v) : "memory"); }
__device__ __forceinline__ void stsm4(uint32_t a, uint32_t r0, uint32_t r1, uint32_t r2, uint32_t r3) {
    asm volatile("stmatrix.sync.aligned.m8n8.x4.shared.b16 [%0], {%1,%2,%3,%4};" ::"r"(a), "r"(r0), "r"(r1), "r"(r2), "r"(r3));
}
__device__ __forceinline__ uint32_t pack2(float lo, float hi) { uint32_t r; asm("cvt.rn.bf16x2.f32 %0, %1, %2;" : "=r"(r) : "f"(hi), "f"(lo)); return r; }
__device__ __forceinline__ uint32_t pack2_relu(float lo, float hi) { uint32_t r; asm("cvt.rn.relu.bf16x2.f32 %0, %1, %2;" : "=r"(r) : "f"(hi), "f"(lo)); return r; }
__device__ __forceinline__ uint32_t hfma2(uint32_t a, uint32_t b, uint32_t c) { uint32_t r; asm("fma.rn.bf16x2 %0, %1, %2, %3;" : "=r"(r) : "r"(a), "r"(b), "r"(c)); return r; }
__device__ __forceinline__ uint32_t hmul2(uint32_t a, uint32_t b) { uint32_t r; asm("mul.rn.bf16x2 %0, %1, %2;" : "=r"(r) : "r"(a), "r"(b)); return r; }
__device__ __forceinline__ float bf_lo(uint32_t v) { return __uint_as_float(v << 16); }
__device__ __forceinline__ float bf_hi(uint32_t v) { return __uint_as_float(v & 0xFFFF0000u); }
__device__ __forceinline__ float bf_round(float v) { return bf_lo(pack2(v, 0.f)); }
__device__ __forceinline__ float ex2(float x) { float r; asm("ex2.approx.ftz.f32 %0, %1;" : "=f"(r) : "f"(x)); return r; }
__device__ __forceinline__ void mma16816(float* d, uint32_t a0, uint32_t a1, uint32_t a2, uint32_t a3, uint32_t b0, uint32_t b1) {
    asm("mma.sync.aligned.m16n8k16.row.col.f32.bf16.bf16.f32 {%0,%1,%2,%3}, {%4,%5,%6,%7}, {%8,%9}, {%0,%1,%2,%3};"
        : "+f"(d[0]), "+f"(d[1]), "+f"(d[2]), "+f"(d[3]) : "r"(a0), "r"(a1), "r"(a2), "r"(a3), "r"(b0), "r"(b1));
}
__device__ __forceinline__ void mma16816_first(float* d, uint32_t a0, uint32_t a1, uint32_t a2, uint32_t a3, uint32_t b0, uint32_t b1) {
    asm volatile("mma.sync.aligned.m16n8k16.row.col.f32.bf16.bf16.f32 {%0,%1,%2,%3}, {%4,%5,%6,%7}, {%8,%9}, {%10,%10,%10,%10};"
        : "=f"(d[0]), "=f"(d[1]), "=f"(d[2]), "=f"(d[3]) : "r"(a0), "r"(a1), "r"(a2), "r"(a3), "r"(b0), "r"(b1), "f"(0.f));
}
__device__ __forceinline__ void mma16816_v(float* d, uint32_t a0, uint32_t a1, uint32_t a2, uint32_t a3, uint32_t b0, uint32_t b1) {
    asm volatile("mma.sync.aligned.m16n8k16.row.col.f32.bf16.bf16.f32 {%0,%1,%2,%3}, {%4,%5,%6,%7}, {%8,%9}, {%0,%1,%2,%3};"
        : "+f"(d[0]), "+f"(d[1]), "+f"(d[2]), "+f"(d[3]) : "r"(a0), "r"(a1), "r"(a2), "r"(a3), "r"(b0), "r"(b1));
}
__device__ __forceinline__ void mma1688(float* d, uint32_t a0, uint32_t a1, uint32_t b0) {
    asm("mma.sync.aligned.m16n8k8.row.col.f32.bf16.bf16.f32 {%0,%1,%2,%3}, {%4,%5}, {%6}, {%0,%1,%2,%3};"
        : "+f"(d[0]), "+f"(d[1]), "+f"(d[2]), "+f"(d[3]) : "r"(a0), "r"(a1), "r"(b0));
}
__device__ __forceinline__ void ldsm4(uint32_t a, uint32_t* r) {
    asm volatile("ldmatrix.sync.aligned.m8n8.x4.shared.b16 {%0,%1,%2,%3}, [%4];" : "=r"(r[0]), "=r"(r[1]), "=r"(r[2]), "=r"(r[3]) : "r"(a));
}
__device__ __forceinline__ void ldsm4t(uint32_t a, uint32_t* r) {
    asm volatile("ldmatrix.sync.aligned.m8n8.x4.trans.shared.b16 {%0,%1,%2,%3}, [%4];" : "=r"(r[0]), "=r"(r[1]), "=r"(r[2]), "=r"(r[3]) : "r"(a));
}
__device__ __forceinline__ float rcp(float x) { float r; asm("rcp.approx.ftz.f32 %0, %1;" : "=f"(r) : "f"(x)); return r; }
__device__ __forceinline__ uint2 ld_relaxed2(const void* p) { uint2 v; asm volatile("ld.relaxed.gpu.global.v2.u32 {%0,%1}, [%2];" : "=r"(v.x), "=r"(v.y) : "l"(p) : "memory"); return v; }
__device__ __forceinline__ void st_relaxed2(void* p, uint32_t x, uint32_t y) { asm volatile("st.relaxed.gpu.global.v2.u32 [%0], {%1,%2};" ::"l"(p), "r"(max(x, 1u)), "r"(max(y, 1u)) : "memory"); }
__device__ __forceinline__ constexpr uint64_t dconst(uint32_t lbo, uint32_t sbo, uint32_t swz) {
    return ((uint64_t)(lbo >> 4) << 16) | ((uint64_t)(sbo >> 4) << 32) | ((uint64_t)swz << 62);
}
__device__ __forceinline__ uint64_t mkdesc(uint32_t addr, uint64_t c) { return c | (uint64_t)((addr & 0x3FFFF) >> 4); }
#define WG_FENCE() asm volatile("wgmma.fence.sync.aligned;" ::: "memory")
#define WG_COMMIT() asm volatile("wgmma.commit_group.sync.aligned;" ::: "memory")
#define WG_WAIT(n) asm volatile("wgmma.wait_group.sync.aligned %0;" ::"n"(n) : "memory")
template <int N> __device__ __forceinline__ void reg_fence(float* d) {
#pragma unroll
    for (int i = 0; i < N; i++) asm volatile("" : "+f"(d[i])::"memory");
}
template <int N> __device__ __forceinline__ void reg_def(float* d) {
#pragma unroll
    for (int i = 0; i < N; i++) asm volatile("" : "=f"(d[i]));
}
template <int N> __device__ __forceinline__ void reg_def(uint32_t* d) {
#pragma unroll
    for (int i = 0; i < N; i++) asm volatile("" : "=r"(d[i]));
}
__device__ __forceinline__ bool is_unset(uint4 v) { return min(min(v.x, v.y), min(v.z, v.w)) == 0u; }
__device__ __forceinline__ uint4 nz4(uint32_t a, uint32_t b, uint32_t c, uint32_t d) { return make_uint4(max(a, 1u), max(b, 1u), max(c, 1u), max(d, 1u)); }
__device__ __forceinline__ void wait_flag(const uint32_t* p, uint32_t target) {
    int n = 0;
    while ((int)(ld_relaxed(p) - target) < 0) { if (++n > SPIN_LIMIT) __trap(); }
    asm volatile("fence.acquire.gpu;" ::: "memory");
}
__device__ __forceinline__ float silu_bf(uint32_t cbits) {
    const float c = __uint_as_float(cbits << 16);
    return bf_round(__fdividef(c, 1.f + fminf(ex2(-1.4426950408889634f * c), 1e30f)));
}
__device__ __forceinline__ void gemv_part(uint32_t wmbuf, int npanel, int wp, int lane) {
    const uint32_t wa = wmbuf + wp * 512 + (8 * (lane >> 4) + (lane & 7)) * 32 + ((lane >> 3) & 1) * 16;
    uint2 B[4];
#pragma unroll
    for (int i = 0; i < 4; i++) { const float2 v = lds2f(wmbuf + 28672 + (wp + 8 * i) * 32 + (lane & 3) * 8); B[i] = make_uint2(__float_as_uint(v.x), __float_as_uint(v.y)); }
#pragma unroll 1
    for (int pn = 0; pn < npanel; pn++) {
        float d[4] = {};
        uint32_t A[16];
#pragma unroll
        for (int i = 0; i < 4; i++) ldsm4t(wa + pn * 14336 + (i < 3 || wp < 4 ? i : 0) * 4096, A + 4 * i);
#pragma unroll
        for (int i = 0; i < 4; i++) mma16816(d, A[4 * i], A[4 * i + 1], A[4 * i + 2], A[4 * i + 3], B[i].x, B[i].y);
        if ((lane & 3) == 0) {
            sts1(wmbuf + 29696 + (wp * 32 + pn * 16 + (lane >> 2)) * 4, __float_as_uint(d[0]));
            sts1(wmbuf + 29696 + (wp * 32 + pn * 16 + 8 + (lane >> 2)) * 4, __float_as_uint(d[2]));
        }
    }
}
__device__ __forceinline__ uint32_t slot_off(int l) { return (l < 3 || l > 6 ? l : l == 6 ? 3 : l + 1) * 16384; }
__device__ __forceinline__ void ln_coeffs(float mean, float msq, uint32_t& r2, uint32_t& n2) {
    const float rs = bf_round(rsqrtf(fmaxf(msq - mean * mean, 0.f) + 1e-5f));
    r2 = pack2(rs, rs);
    n2 = pack2(-mean * rs, -mean * rs);
}

__global__ void __cluster_dims__(2, 1, 1) __launch_bounds__(384, 1) fused_block_kernel(const __grid_constant__ Params p) {
    extern __shared__ __align__(1024) unsigned char smem[];
    const uint32_t sb = (uint32_t)__cvta_generic_to_shared(smem);
    const int tid = threadIdx.x, lane = tid & 31, warp = __shfl_sync(~0u, tid >> 5, 0);
    const int m = blockIdx.x >> 1;
#define kh (j & 1)
    int r, nq;
    {
        int g, i;
        if (m < MAP_S) { g = m < 4 ? 15 : 16; i = m & 3; }
        else if (m < MAP_S + 32) { g = (m - MAP_S) & 7; i = (m - MAP_S) >> 3; }
        else if (m < MAP_S + 60) { i = (m - MAP_S - 32) / 7; g = 8 + (m - MAP_S - 32) - 7 * i; }
        else { g = 16; i = m & 3; }
        r = g; nq = i;
    }
    const int j = opaque(2 * nq + (blockIdx.x & 1)), b = 8 * r + j, fs = 4 * kh + nq;
    const uint32_t sc = r == 16;
#define BAR(i) (sb + M_BAR + 8 * (i))
    if (lane == 0 && warp < 9 && warp != 6 && warp != 7) {
        const int i0 = warp == 8 ? 0 : 8 + 8 * warp, cnt = warp == 0 || warp == 8 ? 1 : warp < 3 ? 2 : 8;
#pragma unroll
        for (int k = 0; k < 8; k++) if (i0 + k != B_WMFULL) mbar_init(BAR(i0 + k), cnt);
        asm volatile("fence.mbarrier_init.release.cluster;" ::: "memory");
        fence_async_smem();
    }

    if (warp < 8) {
        const int w = warp >> 2, wi = warp & 3;
#define COORDS const int t = fresh_tid() & 127, lane = t & 31, q = lane & 3, lr = lane >> 2, ra = 64 * w + 16 * wi + lr; \
        const uint32_t lx = (lane >> 4) ^ (lane & 7), mrow = (64 * w + 16 * wi + ((lane >> 3) & 1) * 8 + (lane & 7)) * 128; \
        (void)q; (void)lr; (void)ra; (void)lx; (void)mrow;
        const int sid = 2 * (j & 3) + w;
#define RUN(k) (!sc || sid == (k))
#define WAIT(i, par) mbar_wait(BAR(i), (par) | sc)
        constexpr uint64_t DB128 = dconst(4096, 1024, 1);
        bar_arrive(9, 384);
        bar_sync(0, 384);
        asm volatile("barrier.cluster.arrive.relaxed.aligned;" ::: "memory");
        asm volatile("setmaxnreg.inc.sync.aligned.u32 224;");
        PROFC(0);
        uint32_t xr[16];
        {
            COORDS
            uint32_t h[112];
            if (RUN(0)) {
                float ds[4] = {}, da[2][4] = {}, db[2][4] = {};
                const uint32_t ONE2 = 0x3F803F80u;
                if (kh == 0) { WAIT(B_WMFULL, 0); gemv_part(sb + OFF_Y + HALF, 1, warp, lane); warp_arrive(BAR(B_GEMV)); }
#pragma unroll
                for (int kb = 0; kb < 7; kb++) {
                    WAIT(B_XFULL + kb, 0);
#pragma unroll
                    for (int k4 = 0; k4 < 4; k4++) ldsm4(sb + OFF_X + mrow + kb * 16384 + (((2 * k4) ^ lx) << 4), h + 16 * kb + 4 * k4);
#pragma unroll
                    for (int k4 = 0; k4 < 4; k4++) {
                        const uint32_t* f = h + 16 * kb + 4 * k4;
                        mma16816(ds, f[0], f[1], f[2], f[3], ONE2, ONE2);
                        mma1688(da[0], f[0], f[1], f[0]); mma1688(db[0], f[0], f[1], f[1]);
                        mma1688(da[1], f[2], f[3], f[2]); mma1688(db[1], f[2], f[3], f[3]);
                    }
                }
#pragma unroll
                for (int i = 0; i < 4; i++) {
                    const int ch = 7 * j + 2 * i + (lane >> 4);
                    ldsm4(sb + OFF_X + mrow + (ch >> 3) * 16384 + (((ch ^ lane) & 7) << 4), xr + 4 * i);
                }
                warp_arrive(BAR(B_XFREE));
                PROFC(27);
                float qa = (lr & 1) ? da[0][1] + da[1][1] : da[0][0] + da[1][0];
                float qb = (lr & 1) ? db[0][3] + db[1][3] : db[0][2] + db[1][2];
                const int src = (lane & ~3) | (lr >> 1);
                qa = __shfl_sync(~0u, qa, src);
                qb = __shfl_sync(~0u, qb, src);
                uint32_t ra2, na2, rb2, nb2;
                ln_coeffs(ds[0] * (1.f / DM), qa * (1.f / DM), ra2, na2);
                ln_coeffs(ds[2] * (1.f / DM), qb * (1.f / DM), rb2, nb2);
#pragma unroll
                for (int i = 0; i < 112; i += 2) { h[i] = hfma2(h[i], ra2, na2); h[i + 1] = hfma2(h[i + 1], rb2, nb2); }
                if (kh == 1) { WAIT(B_WMFULL, 0); gemv_part(sb + OFF_Y + HALF, 2, warp, lane); warp_arrive(BAR(B_GEMV)); }
            } else { reg_def<112>(h); reg_def<16>(xr); }
            PROFC(1);
            if (RUN(1)) {
                float ak[28], av[28], aq[28];
                uint32_t kp[14], vp[14];
                const uint64_t bk0 = mkdesc(sb + OFF_Y, DB128) + kh, bv0 = mkdesc(sb + OFF_Y + HALF, DB128) + kh, bq0 = mkdesc(sb + OFF_X, DB128) + kh;
                uint32_t* kvg = g_kv + (size_t)(b * 2) * 3584 + (8 * w + 2 * wi) * 224 + lane;
                WAIT(B_FULLK, 0);
                WAIT(B_MOD1, 0);
                PROFC(2);
                reg_def<28>(ak);
#pragma unroll
                for (int g4 = 0; g4 < 4; g4++) {
#pragma unroll
                    for (int ks = 7 * g4; ks < 7 * g4 + 7; ks++) {
                        const uint4 st = *(const uint4*)(smem + M_ST + ks * 64 + q * 16);
                        h[4 * ks] = hfma2(h[4 * ks], st.x, st.y); h[4 * ks + 1] = hfma2(h[4 * ks + 1], st.x, st.y);
                        h[4 * ks + 2] = hfma2(h[4 * ks + 2], st.z, st.w); h[4 * ks + 3] = hfma2(h[4 * ks + 3], st.z, st.w);
                    }
                    WG_FENCE();
#pragma unroll
                    for (int ks = 7 * g4; ks < 7 * g4 + 7; ks++) wgmma_rs_56<1>(ak, h[4 * ks], h[4 * ks + 1], h[4 * ks + 2], h[4 * ks + 3], bk0 + ks * 128, ks != 0);
                }
                WG_COMMIT();
                PROFC(3);
                WAIT(B_FULLV, 0);
                reg_def<28>(av);
                WG_FENCE();
#pragma unroll
                for (int ks = 0; ks < 8; ks++) wgmma_rs_56<1>(av, h[4 * ks], h[4 * ks + 1], h[4 * ks + 2], h[4 * ks + 3], bv0 + ks * 128, ks != 0);
                WG_COMMIT();
                WG_WAIT(1);
                reg_fence<28>(ak);
#pragma unroll
                for (int g = 0; g < 7; g++) {
                    kp[2 * g] = pack2(ak[4 * g], ak[4 * g + 1]); kp[2 * g + 1] = pack2(ak[4 * g + 2], ak[4 * g + 3]);
                    kvg[g * 32] = kp[2 * g]; kvg[224 + g * 32] = kp[2 * g + 1];
                }
                warp_arrive(BAR(B_PUB));
                PROFC(4);
                WG_FENCE();
#pragma unroll
                for (int ks = 8; ks < 28; ks++) wgmma_rs_56<1>(av, h[4 * ks], h[4 * ks + 1], h[4 * ks + 2], h[4 * ks + 3], bv0 + ks * 128, 1);
                WG_COMMIT();
                WAIT(B_FULLQ, 0);
                reg_def<28>(aq);
                WG_FENCE();
#pragma unroll
                for (int ks = 0; ks < 8; ks++) wgmma_rs_56<1>(aq, h[4 * ks], h[4 * ks + 1], h[4 * ks + 2], h[4 * ks + 3], bq0 + ks * 128, ks != 0);
                WG_COMMIT();
                WG_WAIT(1);
                reg_fence<28>(av);
#pragma unroll
                for (int g = 0; g < 7; g++) {
                    vp[2 * g] = pack2(av[4 * g], av[4 * g + 1]); vp[2 * g + 1] = pack2(av[4 * g + 2], av[4 * g + 3]);
                    kvg[3584 + g * 32] = vp[2 * g]; kvg[3584 + 224 + g * 32] = vp[2 * g + 1];
                }
                warp_arrive(BAR(B_PUB + 1));
                PROFC(5);
                WG_FENCE();
#pragma unroll
                for (int ks = 8; ks < 28; ks++) wgmma_rs_56<1>(aq, h[4 * ks], h[4 * ks + 1], h[4 * ks + 2], h[4 * ks + 3], bq0 + ks * 128, 1);
                WG_COMMIT();
                WAIT(B_PUB + 1, 0);
                const uint32_t ko = sb + OFF_Y + Y_KOWN + (8 * w + 2 * wi) * 896 + lane * 4;
                const uint32_t qo = sb + OFF_Y + Y_Q + (8 * w + 2 * wi) * 1024 + lane * 4;
#pragma unroll
                for (int g = 0; g < 7; g++) {
                    sts1(ko + g * 128, kp[2 * g]); sts1(ko + 896 + g * 128, kp[2 * g + 1]);
                    sts1(ko + (Y_VOWN - Y_KOWN) + g * 128, vp[2 * g]); sts1(ko + (Y_VOWN - Y_KOWN) + 896 + g * 128, vp[2 * g + 1]);
                }
                WG_WAIT(0);
                reg_fence<28>(aq);
                __syncwarp();
                if (lane < 3 && w == 1) mbar_arrive(BAR(B_EMPTY + lane));
#pragma unroll
                for (int g = 0; g < 7; g++) {
                    const uint32_t q0 = pack2(aq[4 * g], aq[4 * g + 1]), q1 = pack2(aq[4 * g + 2], aq[4 * g + 3]);
                    if (g == 3) {
                        sts1(qo + 3 * 128, q < 2 ? q0 : 0u); sts1(qo + 1024 + 3 * 128, q < 2 ? q1 : 0u);
                        sts1(qo + 4 * 128, q < 2 ? 0u : q0); sts1(qo + 1024 + 4 * 128, q < 2 ? 0u : q1);
                    } else {
                        const int ch = g < 3 ? g : g + 1;
                        sts1(qo + ch * 128, q0); sts1(qo + 1024 + ch * 128, q1);
                    }
                }
                if (!sc) bar_sync(3, 256);
            }
        }
        PROFC(6);
        WAIT(B_KRFULL, 0);
        PROFC(7);
        if (RUN(2)) {
#pragma unroll 1
            for (int hf = sc; hf < 2; hf++) {
                COORDS
                float s[136];
                float na = 0.f, nb = 0.f;
                const float CS = 0.18898223650461361f * 1.4426950408889634f;
                const int kg0 = 8 * hf + 2 * wi;
                const int pmin = 16 - 8 * r - 4 * hf - wi;
                const float NEG = __int_as_float(0xFF800000);
                {
                    uint32_t F[8];
                    const uint32_t qa = sb + OFF_Y + Y_Q + (kg0 + ((lane >> 3) & 1)) * 1024 + (4 * w + (lane >> 4)) * 128 + (lane & 7) * 16;
                    ldsm4(qa, F); ldsm4(qa + 256, F + 4);
                    uint32_t ka = sb + OFF_Y + Y_K + kg0 * 896 + (3 * w + (lane >> 3)) * 128 + (lane & 7) * 16;
#pragma unroll
                    for (int g = 0; g < 34; g++) {
                        uint32_t B[4];
                        if (g >= 12 && g % 4 == 0) ka += __float_as_uint(s[4 * (g - 12)]) & p.zero;
                        ldsm4(ka + g * 896, B);
                        mma16816_first(s + 4 * g, F[0], F[1], F[2], F[3], B[0], B[1]);
                        mma16816_v(s + 4 * g, F[4], F[5], F[6], F[7], B[2], B[3]);
                    }
                    const bool c0 = 2 * q > lr, c1 = 2 * q + 1 > lr;
                    if (!c0) { s[0] = NEG; s[6] = NEG; }
                    if (!c1) { s[1] = NEG; s[7] = NEG; }
                    s[2] = NEG; s[3] = NEG;
                    if (c0) { s[128] = NEG; s[134] = NEG; }
                    if (c1) { s[129] = NEG; s[135] = NEG; }
                    s[132] = NEG; s[133] = NEG;
                    float ma = NEG, mb = NEG;
#pragma unroll
                    for (int pp = 0; pp < 17; pp++) {
                        const float* e = s + 8 * pp;
                        const float bias = pp < pmin ? NEG : 0.f;
                        ma = fmaxf(ma, fmaxf(fmaxf(e[0], e[1]), fmaxf(e[4], e[5])) + bias);
                        mb = fmaxf(mb, fmaxf(fmaxf(e[2], e[3]), fmaxf(e[6], e[7])) + bias);
                    }
                    ma = fmaxf(ma, __shfl_xor_sync(~0u, ma, 1)); mb = fmaxf(mb, __shfl_xor_sync(~0u, mb, 1));
                    ma = fmaxf(ma, __shfl_xor_sync(~0u, ma, 2)); mb = fmaxf(mb, __shfl_xor_sync(~0u, mb, 2));
                    na = -ma * CS; nb = -mb * CS;
                }
                PROFC(8 + 3 * hf);
                {
                    if (hf == 0) mbar_wait(BAR(B_VRFULL), 0);
                    float o[16] = {}, rs[4] = {};
                    const uint32_t va = sb + OFF_Y + Y_VR + (kg0 + ((lane >> 3) & 1)) * 896 + (3 * w + (lane >> 4)) * 128 + (lane & 7) * 16;
#pragma unroll
                    for (int pp = 0; pp < 17; pp++) {
                        uint32_t B[8];
                        const uint32_t v = va + pp * 1792 + (pp == 16 || (pp >= 9 && kg0 + 2 * pp >= 32) ? Y_VOWN - 32 * 896 : 0);
                        ldsm4t(v, B); ldsm4t(v + 256, B + 4);
                        float e[8];
#pragma unroll
                        for (int i = 0; i < 8; i++) e[i] = ex2(fmaf(s[8 * pp + i], CS, ((i & 2) ? nb : na) + (pp < pmin ? NEG : 0.f)));
                        const uint32_t p0 = pack2(e[0], e[1]), p1 = pack2(e[2], e[3]), p2 = pack2(e[4], e[5]), p3 = pack2(e[6], e[7]);
                        mma16816(rs, p0, p1, p2, p3, 0x3F803F80u, 0x3F803F80u);
#pragma unroll
                        for (int g = 0; g < 4; g++) mma16816(o + 4 * g, p0, p1, p2, p3, B[2 * g], B[2 * g + 1]);
                    }
                    PROFC(9 + 3 * hf);
                    const float ia = rcp(rs[0]), ib = rcp(rs[2]);
                    uint32_t* og = g_o + (size_t)(2 * r + hf) * 14336 + (7 * j + 3 * w) * 256 + wi * 64 + lane;
#pragma unroll
                    for (int g = 0; g < 4; g++) {
                        if ((g == 3 - 3 * w) ? ((q >> 1) == w) : true) {
                            og[g * 256] = pack2(o[4 * g] * ia, o[4 * g + 1] * ia);
                            og[g * 256 + 32] = pack2(o[4 * g + 2] * ib, o[4 * g + 3] * ib);
                        }
                    }
                    warp_arrive(BAR(B_PUB + 2 + hf));
                    PROFC(10 + 3 * hf);
                }
            }
        }
        uint32_t x1p[14];
        COORDS
        constexpr uint64_t DT = dconst(1024, 128, 0);
        if (RUN(4)) {
            float ac[28];
            const uint64_t ad = mkdesc(sb + (w ? OFF_Y + HALF : OFF_X), DT), bd = mkdesc(sb + OFF_X + HALF, DB128) + kh;
            WAIT(B_WOFULL, 0);
            WAIT(B_MOD2, 0);
            WAIT(B_GFULL + w, 0);
            PROFC(28);
            reg_def<28>(ac);
#pragma unroll 1
            for (int u = 0; u < 4; u++) {
                WG_FENCE();
#pragma unroll
                for (int i = 0; i < 7; i++) wgmma_ss_56<1>(ac, ad + (7 * u + i) * 128, bd + (7 * u + i) * 128, (u | i) != 0);
            }
            WG_COMMIT();
            WG_WAIT(0);
            reg_fence<28>(ac);
            PROFC(14);
            __syncwarp();
            if (lane < 3) mbar_arrive(BAR(B_EMPTY + 3 + lane));
            if (lane < 3 && w == 0) mbar_arrive(BAR(B_EMPTY + lane));
            float s1a = 0.f, s2a = 0.f, s1b = 0.f, s2b = 0.f;
            uint32_t* xo = g_x1 + (size_t)(2 * r + w) * 14336 + 7 * j * 256 + wi * 64 + lane;
#pragma unroll
            for (int g = 0; g < 7; g++) {
                const float2 ga = *(const float2*)(smem + M_G + (8 * g + 2 * q) * 4);
                x1p[2 * g] = pack2(fmaf(ga.x, ac[4 * g], bf_lo(xr[2 * g])), fmaf(ga.y, ac[4 * g + 1], bf_hi(xr[2 * g])));
                x1p[2 * g + 1] = pack2(fmaf(ga.x, ac[4 * g + 2], bf_lo(xr[2 * g + 1])), fmaf(ga.y, ac[4 * g + 3], bf_hi(xr[2 * g + 1])));
                xo[g * 256] = x1p[2 * g]; xo[g * 256 + 32] = x1p[2 * g + 1];
                const float u0 = bf_lo(x1p[2 * g]), u1 = bf_hi(x1p[2 * g]), u2 = bf_lo(x1p[2 * g + 1]), u3 = bf_hi(x1p[2 * g + 1]);
                s1a += u0 + u1; s2a += u0 * u0 + u1 * u1; s1b += u2 + u3; s2b += u2 * u2 + u3 * u3;
            }
            float ka = (q & 1) ? s2a : s1a, kb2 = (q & 1) ? s2b : s1b;
            ka += __shfl_xor_sync(~0u, (q & 1) ? s1a : s2a, 1); kb2 += __shfl_xor_sync(~0u, (q & 1) ? s1b : s2b, 1);
            const float kk = ((q & 2) ? kb2 : ka) + __shfl_xor_sync(~0u, (q & 2) ? ka : kb2, 2);
            ((float*)g_st)[(((2 * r + w) * 8 + j) * 64 + 16 * wi + lr + 4 * (q & 2)) * 2 + (q & 1)] = kk;
            __syncwarp();
            if (lane < 2) mbar_arrive(BAR(B_PUB + 4 + w));
        } else reg_def<14>(x1p);
        PROFC(15);
        uint32_t h2a[32], h2b[24];
        if (RUN(6)) {
            const int fa = 224 * fs + ((fs & 1) ? 96 : 0), fb = 224 * fs + ((fs & 1) ? 0 : 128);
            uint32_t* h2g = g_h2 + (size_t)r * (224 * 512) + (8 * w + 2 * wi) * 32 + lane;
            const uint64_t a0 = mkdesc(sb + OFF_Y + w * HALF, DT);
            const int s0 = sc ? 12 : 0;
            {
                WAIT(B_GFULL + 2 + w, 0);
                PROFC(16);
                float2 sa = make_float2(0.f, 0.f), sbb = sa;
#pragma unroll
                for (int jj = 0; jj < 8; jj++) {
                    const float2 u = lds2f(sb + OFF_X + X_STAT + w * 4096 + (jj * 64 + 16 * wi + lr) * 8), v = lds2f(sb + OFF_X + X_STAT + w * 4096 + (jj * 64 + 16 * wi + lr + 8) * 8);
                    sa.x += u.x; sa.y += u.y; sbb.x += v.x; sbb.y += v.y;
                }
                warp_arrive(BAR(B_EMPTY + 6));
                uint32_t ra2, na2, rb2, nb2;
                ln_coeffs(sa.x * (1.f / DM), sa.y * (1.f / DM), ra2, na2);
                ln_coeffs(sbb.x * (1.f / DM), sbb.y * (1.f / DM), rb2, nb2);
                const uint32_t ha = sb + OFF_Y + w * HALF + (lane >> 4) * 1024 + (2 * wi + ((lane >> 3) & 1)) * 128 + (lane & 7) * 16;
                const uint32_t sta = sb + M_ST + q * 16;
                auto prep = [&](int s, uint32_t* f) {
#pragma unroll
                    for (int i = 0; i < 2; i++) {
                        uint32_t x[4];
                        ldsm4(ha + (2 * s + i) * 2048, x);
                        const uint4 st = lds4(sta + (2 * s + i) * 64);
                        f[4 * i] = hfma2(hfma2(x[0], ra2, na2), st.x, st.y); f[4 * i + 1] = hfma2(hfma2(x[1], rb2, nb2), st.x, st.y);
                        f[4 * i + 2] = hfma2(hfma2(x[2], ra2, na2), st.z, st.w); f[4 * i + 3] = hfma2(hfma2(x[3], rb2, nb2), st.z, st.w);
                        stsm4(ha + (2 * s + i) * 2048, f[4 * i], f[4 * i + 1], f[4 * i + 2], f[4 * i + 3]);
                    }
                };
                float ac[128];
                uint32_t fr[2][8];
                reg_def<128>(ac);
                prep(s0, fr[0]);
                PROFC(17);
                int sl = 0, prev = 0;
#pragma unroll 1
                for (int s2 = s0; s2 < 14; s2 += 2) {
#pragma unroll
                    for (int e = 0; e < 2; e++) {
                        const int s = s2 + e;
                        const uint32_t* f = fr[e];
                        WAIT(B_FULL + sl, s >= 7);
                        const uint64_t bd = mkdesc(sb + slot_off(sl), DB128);
                        WG_FENCE();
                        wgmma_rs_256<1>(ac, f[0], f[1], f[2], f[3], bd, s != 0);
                        wgmma_rs_256<1>(ac, f[4], f[5], f[6], f[7], bd + 128, 1);
                        WG_COMMIT();
                        WG_WAIT(1);
                        if (s > 0) warp_arrive(BAR(B_EMPTY + prev));
                        if (s < 13) prep(s + 1, fr[e ^ 1]);
                        prev = sl; sl = sl == 6 ? 0 : sl + 1;
                    }
                }
                fence_async_smem();
                WG_WAIT(0);
                reg_fence<128>(ac);
                warp_arrive(BAR(B_EMPTY + 6));
                PROFC(18);
#pragma unroll
                for (int g = 0; g < 16; g++) {
                    h2a[2 * g] = hmul2(pack2_relu(ac[4 * g], ac[4 * g + 1]), pack2(ac[64 + 4 * g], ac[64 + 4 * g + 1]));
                    h2a[2 * g + 1] = hmul2(pack2_relu(ac[4 * g + 2], ac[4 * g + 3]), pack2(ac[64 + 4 * g + 2], ac[64 + 4 * g + 3]));
                    h2g[(fa / 8 + g) * 512] = h2a[2 * g]; h2g[(fa / 8 + g) * 512 + 32] = h2a[2 * g + 1];
                }
                warp_arrive(BAR(B_PUB + 6));
                bar_sync(1 + w, 128);
            }
            PROFC(19);
            {
                float ac[96];
                reg_def<96>(ac);
                int sl = 0, prev = 0;
#pragma unroll 1
                for (int s = s0; s < 14; s++) {
                    WAIT(B_FULL + sl, s >= 7);
                    const uint64_t ad = a0 + s * 256, bd = mkdesc(sb + slot_off(sl), dconst(2048, 512, 2));
                    WG_FENCE();
                    wgmma_ss_192<1>(ac, ad, bd, s != 0);
                    wgmma_ss_192<1>(ac, ad + 128, bd + 64, 1);
                    WG_COMMIT();
                    if (s > 0) { WG_WAIT(1); warp_arrive(BAR(B_EMPTY + prev)); }
                    prev = sl; sl = sl == 6 ? 0 : sl + 1;
                }
                WG_WAIT(0);
                reg_fence<96>(ac);
                __syncwarp();
                if (lane < 6) mbar_arrive(BAR(B_EMPTY + 6 + lane));
                asm volatile("barrier.cluster.wait.aligned;" ::: "memory");
                if (lane == 0 && !sc) {
                    uint32_t rb;
                    asm volatile("mapa.shared::cluster.u32 %0, %1, %2;" : "=r"(rb) : "r"(BAR(B_PEER)), "r"(kh ^ 1));
                    asm volatile("mbarrier.arrive.relaxed.cluster.shared::cluster.b64 _, [%0];" ::"r"(rb) : "memory");
                }
                PROFC(20);
#pragma unroll
                for (int g = 0; g < 12; g++) {
                    h2b[2 * g] = hmul2(pack2_relu(ac[4 * g], ac[4 * g + 1]), pack2(ac[48 + 4 * g], ac[48 + 4 * g + 1]));
                    h2b[2 * g + 1] = hmul2(pack2_relu(ac[4 * g + 2], ac[4 * g + 3]), pack2(ac[48 + 4 * g + 2], ac[48 + 4 * g + 3]));
                    h2g[(fb / 8 + g) * 512] = h2b[2 * g]; h2g[(fb / 8 + g) * 512 + 32] = h2b[2 * g + 1];
                }
                warp_arrive(BAR(B_PUB + 7));
            }
        } else { reg_def<32>(h2a); reg_def<24>(h2b); }
        PROFC(21);
        if (RUN(7)) {
            float ac[56];
            reg_def<56>(ac);
            constexpr uint64_t DAN = dconst(2048, 128, 0);
#pragma unroll
            for (int e = 0; e < 4; e++) {
                WAIT(B_FULL + e, 0);
                const uint64_t bd = mkdesc(sb + slot_off(e), DB128);
                const uint32_t* hh = e < 2 ? h2a + 16 * e : h2b + 16 * (e - 2);
                WG_FENCE();
#pragma unroll
                for (int k = 0; k < (e < 3 ? 4 : 2); k++) wgmma_rs_112<1>(ac, hh[4 * k], hh[4 * k + 1], hh[4 * k + 2], hh[4 * k + 3], bd + (k >> 1) * 512 + (k & 1) * 128, (e | k) != 0);
                WG_COMMIT();
                if (e > 0) { WG_WAIT(1); warp_arrive(BAR(B_EMPTY + e - 1)); }
            }
            PROFC(22);
            int sl = 4, prev = 3;
#pragma unroll 1
            for (int e = 4; e < 25; e++) {
                WAIT(B_FULL + sl, e >= 12 && e < 24);
                if (e == 16) PROFC(23);
                const uint32_t sa = sb + slot_off(sl);
                const uint64_t ad = mkdesc(sa + 8192 + w * 1024, DAN), bd = mkdesc(sa, DB128);
                WG_FENCE();
                wgmma_ss_112<1>(ac, ad, bd, 1);
                wgmma_ss_112<1>(ac, ad + 256, bd + 128, 1);
                WG_COMMIT();
                if (e < 14) { WG_WAIT(1); warp_arrive(BAR(B_EMPTY + prev)); }
                prev = sl; sl = sl == 11 ? 0 : sl + 1;
            }
            mbar_wait_cluster(BAR(B_PEER), sc);
            WG_WAIT(0);
            reg_fence<56>(ac);
            PROFC(24);
            uint32_t rdst, rbar;
            asm volatile("mapa.shared::cluster.u32 %0, %1, %2;" : "=r"(rdst) : "r"(sb + OFF_Y + (5 + w) * 16384 + t * 16), "r"(kh ^ 1 ^ sc));
            asm volatile("mapa.shared::cluster.u32 %0, %1, %2;" : "=r"(rbar) : "r"(BAR(B_XCH + w)), "r"(kh ^ 1 ^ sc));
#pragma unroll
            for (int g = 0; g < 7; g++) {
                const float v0 = kh ? ac[4 * g] : ac[28 + 4 * g], v1 = kh ? ac[4 * g + 1] : ac[28 + 4 * g + 1];
                const float v2 = kh ? ac[4 * g + 2] : ac[28 + 4 * g + 2], v3 = kh ? ac[4 * g + 3] : ac[28 + 4 * g + 3];
                if (!sc) asm volatile("st.async.shared::cluster.mbarrier::complete_tx::bytes.v4.f32 [%0], {%1,%2,%3,%4}, [%5];"
                             ::"r"(rdst + g * 2048), "f"(v0), "f"(v1), "f"(v2), "f"(v3), "r"(rbar) : "memory");
            }
            mbar_wait_cluster(BAR(B_XCH + w), sc);
            PROFC(25);
            bf16* og = (sc ? (bf16*)(g_h2 + 16 * 224 * 512) : p.out + (size_t)128 * r * DM) + (size_t)ra * DM + 56 * j + 2 * q;
#pragma unroll
            for (int g = 0; g < 7; g++) {
                const uint4 rv = *(const uint4*)(smem + OFF_Y + (5 + w) * 16384 + t * 16 + g * 2048);
                const float2 gb = *(const float2*)(smem + M_G + 224 + (8 * g + 2 * q) * 4);
                const float v0 = (kh ? ac[28 + 4 * g] : ac[4 * g]) + __uint_as_float(rv.x), v1 = (kh ? ac[28 + 4 * g + 1] : ac[4 * g + 1]) + __uint_as_float(rv.y);
                const float v2 = (kh ? ac[28 + 4 * g + 2] : ac[4 * g + 2]) + __uint_as_float(rv.z), v3 = (kh ? ac[28 + 4 * g + 3] : ac[4 * g + 3]) + __uint_as_float(rv.w);
                *(uint32_t*)(og + 8 * g) = pack2(fmaf(gb.x, v0, bf_lo(x1p[2 * g])), fmaf(gb.y, v1, bf_hi(x1p[2 * g])));
                *(uint32_t*)(og + 8 * DM + 8 * g) = pack2(fmaf(gb.x, v2, bf_lo(x1p[2 * g + 1])), fmaf(gb.y, v3, bf_hi(x1p[2 * g + 1])));
            }
        }
        PROFC(26);
        warp_arrive(BAR(B_DONE));
    } else {
        const int lane = fresh_tid() & 31;
        const bool early = kh == 0, gemv = r < 14;
        const int mcol = early ? 16 * (4 * r + nq) : 2 * DM + 32 * (4 * r + nq);
        const uint32_t wmbuf = sb + OFF_Y + HALF;
        const int fa = 224 * fs + ((fs & 1) ? 96 : 0), fb = 224 * fs + ((fs & 1) ? 0 : 128);
        asm volatile("setmaxnreg.dec.sync.aligned.u32 56;");
        if (warp == 9) {
#pragma unroll
            for (int i = 56; i < 63; i++) init_e(BAR(i), 1);
            fence_async_smem();
        }
        if (warp == 8) { init_e(BAR(B_WMFULL), 2); fence_async_smem(); }
        bar_arrive(0, 384);
        asm volatile("barrier.cluster.arrive.relaxed.aligned;" ::: "memory");
        uint32_t target = 0;
        if (warp == 8) {
            if (!sc) {
                expect_e(BAR(B_WMFULL), gemv ? 28672 >> early : 0);
                if (early && gemv) { tma3_e(wmbuf, &p.wm, mcol, 0, 0, BAR(B_WMFULL)); tma3_e(wmbuf + 7168, &p.wm, mcol, 224, 0, BAR(B_WMFULL)); }
#pragma unroll 1
                for (int kb = 0; kb < 7; kb++) {
                    expect_e(BAR(B_XFULL + kb), 16384);
                    tma3_e(sb + OFF_X + kb * 16384, &p.xm, 64 * kb, 128 * r, 0, BAR(B_XFULL + kb));
                }
            }
#pragma unroll 1
            for (int mt = 0; mt < 4; mt++) {
                if (mt == 1) {
                    if (!early && gemv) {
#pragma unroll 1
                        for (int k = 0; k < 4; k++) tma3_e(wmbuf + k * 7168, &p.wm, mcol + (k >> 1) * 16, (k & 1) * 224, 0, BAR(B_WMFULL));
                    }
                    bar_sync(9, 384);
                    if (sc) return;
                    mbar_wait(BAR(B_MOD1), 0);
                    mbar_wait(BAR(B_WMFREE), 0);
                }
                if (mt == 2) mbar_wait(BAR(B_XFREE), 0);
                if (mt == 3) mbar_wait(BAR(B_VRFULL), 0);
                const uint32_t bar = BAR(mt == 3 ? B_WOFULL : B_FULLK + mt), dst = sb + (mt < 2 ? OFF_Y : OFF_X) + (mt & 1) * HALF;
                const int c0 = (mt < 2 ? DM + DM * mt : 0) + 56 * j - 8 * kh;
                if (!sc) {
                    expect_e(bar, HALF);
                    tma3_e(dst, mt == 3 ? &p.wo : &p.qkv, c0, 0, 0, bar);
                    tma3_e(dst + HALF / 2, mt == 3 ? &p.wo : &p.qkv, c0, 224, 0, bar);
                }
            }
            expect_e(BAR(B_XCH), 14336);
            expect_e(BAR(B_XCH + 1), 14336);
        } else {
            if (warp == 10 && lane == 0 && !sc) {
                const uint32_t ticket = atomicAdd(&g_ticket, 1u);
                l2_prefetch((const char*)p.wqkv + (size_t)b * 9408, 9408);
                sts1(sb + M_EPOCH, ticket / NCTA);
            }
            if (warp == 11) {
#pragma unroll
                for (int i = 0; i < 8; i++) {
                    const int wd = lane + 32 * i;
                    const uint32_t cb = i < 7 ? __ldg((const uint32_t*)p.c + wd) : 0u;
                    sts1(wmbuf + 28672 + (wd >> 3) * 32 + (wd & 3) * 8 + (wd & 4), pack2(silu_bf(cb & 0xFFFFu), silu_bf(cb >> 16)));
                }
            }
            bar_sync(9, 384);
            if (sc) return;
            target = lds1(sb + M_EPOCH) + 1;
            const uint32_t tag = target & 0xFFFFu;
            if (warp == 11) {
                warp_arrive(BAR(B_WMFULL));
                mbar_wait(BAR(B_GEMV), 0);
                float sum = 0.f;
#pragma unroll
                for (int i = 0; i < 8; i++) sum += *(const float*)(smem + OFF_Y + HALF + 29696 + (i * 32 + (early ? lane & 15 : lane)) * 4);
                const uint32_t word = (pack2(sum, 0.f) << 16) | tag;
                if (gemv) {
                    uint32_t* mg = g_mod + mcol + (early ? (lane & 15) + (lane >> 4) * 4 * 6 * DM : lane);
#pragma unroll
                    for (int i = 0; i < 8; i++) if (i < 4 || !early) st_relaxed(mg + i * 6 * DM, word);
                }
                warp_arrive(BAR(B_WMFREE));
            }
            const uint4* modp = (const uint4*)g_mod + (r & 7) * (6 * DM / 4);
            const bool p2 = warp == 11;
            mbar_wait(BAR(p2 ? B_PUB : B_XFULL + 4), 0);
#pragma unroll 1
            for (int it = p2 ? 0 : warp - 9; it < (p2 ? 2 : warp - 8); it++) {
                const int i0 = lane + 32 * it, imax = p2 ? 251 : 223;
                uint4 v[4];
#pragma unroll 1
                for (int n = 0;; n++) {
                    uint32_t bad = 0;
#pragma unroll
                    for (int k = 0; k < 4; k++) {
                        const int i = min(i0 + 64 * k, imax);
                        v[k] = ld_relaxed4(modp + (i < 224 ? (p2 ? 336 : 0) + i : (i < 238 ? 14 * j + i : 14 * j + i + 322)));
                        bad |= (v[k].x ^ tag) | (v[k].y ^ tag) | (v[k].z ^ tag) | (v[k].w ^ tag);
                    }
                    if (!(bad & 0xFFFFu)) break;
                    if (n > SPIN_LIMIT) __trap();
                }
#pragma unroll
                for (int k = 0; k < 4; k++) {
                    const int i = min(i0 + 64 * k, imax);
                    if (i < 224) {
                        const int isc = i >= 112, c4 = i - 112 * isc;
                        const float one = isc ? 1.f : 0.f;
                        const uint32_t a = sb + M_ST + (c4 >> 2) * 64 + (c4 & 1) * 32 + (c4 & 2) * 4 + (isc ? 0 : 4);
                        sts1(a, pack2(bf_hi(v[k].x) + one, bf_hi(v[k].y) + one));
                        sts1(a + 16, pack2(bf_hi(v[k].z) + one, bf_hi(v[k].w) + one));
                    } else {
                        sts4(sb + M_G + (i - 224) * 16, make_uint4(v[k].x & 0xFFFF0000u, v[k].y & 0xFFFF0000u, v[k].z & 0xFFFF0000u, v[k].w & 0xFFFF0000u));
                    }
                }
                warp_arrive(BAR(p2 ? B_MOD2 : B_MOD1));
            }
            if (warp == 9) {
#pragma unroll 1
                for (int kv = 0; kv < 2; kv++) {
                    mbar_wait(BAR(B_PUB + kv), 0);
                    if (lane >= 1 && lane <= 2 && r >= lane) wait_flag(g_flag + kv * 128 + b - 8 * lane, target);
                    __syncwarp();
                    fence_async_global();
                    const uint32_t dst = sb + OFF_Y + (kv ? Y_VR : Y_K);
                    expect_e(BAR(B_KRFULL + kv), r >= 2 ? 28672 : r == 1 ? 14336 : 0);
                    if (r >= 2) bulk_e(dst, g_kv + (size_t)((b - 16) * 2 + kv) * 3584, 14336, BAR(B_KRFULL + kv));
                    if (r >= 1) bulk_e(dst + 14336, g_kv + (size_t)((b - 8) * 2 + kv) * 3584, 14336, BAR(B_KRFULL + kv));
                }
            } else if (warp == 11) {
                mbar_wait(BAR(B_VRFULL), 0);
                if (lane == 0) {
                    l2_prefetch((const char*)p.wg + (size_t)b * 12544, 12544);
                    l2_prefetch((const char*)p.wu + (size_t)b * 12544, 12544);
                    l2_prefetch((const char*)p.wd + (size_t)b * 12544, 12544);
                }
                __syncwarp();
            }
        }
        if (warp == 8 || warp == 11) {
            const int sec = warp == 11;
            int sl = 0;
#pragma unroll 1
            for (int s = 0; s < 28; s++) {
                if (s >= 1 && s < 6) mbar_wait(BAR(B_FULL + s - 1), 0);
                const bool pa = s < 14;
                const uint32_t half = pa ? 8192 : 6144;
                mbar_wait(BAR(B_EMPTY + sl), (s >= 7 && s < 14) || s >= 21);
                expect_e(BAR(B_FULL + sl), half);
                tma3_e(sb + slot_off(sl) + sec * half, &p.ga + (pa ? 0 : 2) + sec, 0, 32 * (pa ? s : s - 14), pa ? fa >> 6 : fb >> 5, BAR(B_FULL + sl));
                sl = sl == 6 ? 0 : sl + 1;
            }
            if (!sec) PROFH(3);
#pragma unroll 1
            for (int e = 0; e < 4; e++) {
                const uint32_t dst = sb + slot_off(e) + sec * 8192, bar = BAR(B_FULL + e);
                const int f = (e < 2 ? fa : fb) + 64 * (e & 1) + 32 * sec;
                mbar_wait(BAR(B_EMPTY + e), 0);
                expect_e(bar, e == 3 && sec ? 0 : 8192);
                if (!(e == 3 && sec)) { tma3_e(dst, &p.dn, 0, nq, f, bar); tma3_e(dst + 4096, &p.dn, 64, nq, f, bar); }
            }
            sl = 4;
            int e = 4;
#pragma unroll 1
            for (int grp = 0; grp < 6; grp++) {
                const bool pa = grp < 3;
                int sidx = pa ? grp : grp - 3;
                sidx += sidx >= nq;
                const int ofs = 4 * kh + sidx;
                int f = 224 * ofs + ((ofs & 1) ? (pa ? 96 : 0) : (pa ? 0 : 128));
                if (sec && (grp == 0 || grp == 3)) { mbar_wait(BAR(B_HRDY + !pa), 0); fence_async_global(); }
#pragma unroll 1
                for (int k = pa ? 0 : 1; k < 4; k++, e++, f += 32) {
                    const uint32_t dst = sb + slot_off(sl), bar = BAR(B_FULL + sl);
                    mbar_wait(BAR(B_EMPTY + sl), e >= 12 && e < 24);
                    expect_e(bar, 8192);
                    if (!sec) { tma3_e(dst, &p.dn, 0, nq, f, bar); tma3_e(dst + 4096, &p.dn, 64, nq, f, bar); }
                    else bulk_e(dst + 8192, g_h2 + (size_t)r * (224 * 512) + f * 64, 8192, bar);
                    sl = sl == 11 ? 0 : sl + 1;
                }
            }
            if (!sec) PROFH(4);
            mbar_wait(BAR(B_DONE), 0);
        } else if (warp == 9) {
#pragma unroll
            for (int ev = 0; ev < 4; ev++) expect_e(BAR(B_GFULL + ev), ev < 2 ? HALF : HALF + 4096);
            mbar_wait(BAR(B_PUB + 2), 0);
            const uint32_t* fp = g_flag + (2 + (lane >> 3)) * 128 + 8 * r + (lane & 7);
            const uint32_t* src = g_ox + (size_t)2 * r * 14336;
            const float2* ssrc = g_st + 2 * r * 512;
#pragma unroll 1
            for (int n = 0, ev = 0; ev < 4; n++) {
                if (ev == 1) mbar_wait(BAR(B_PUB + 3), 0);
                uint32_t ok = __ballot_sync(~0u, (int)(ld_relaxed(fp) - target) >= 0) >> (8 * ev);
                while ((ok & 0xFFu) == 0xFFu) {
                    asm volatile("fence.acquire.gpu;" ::: "memory");
                    fence_async_global();
                    const uint32_t bar = BAR(B_GFULL + ev);
                    bulk_e(sb + (ev == 0 ? OFF_X : OFF_Y + (ev & 1) * HALF), src + (ev >> 1) * (34 * 14336) + (ev & 1) * 14336, HALF, bar);
                    if (ev >= 2) bulk_e(sb + OFF_X + X_STAT + (ev & 1) * 4096, ssrc + (ev & 1) * 512, 4096, bar);
                    if (ev) PROFH(4 + ev);
                    ev++; ok >>= 8;
                }
                if (n > SPIN_LIMIT) __trap();
            }
#pragma unroll 1
            for (int ps = 0; ps < 2; ps++) {
                mbar_wait(BAR(B_PUB + 6 + ps), 0);
                if (lane < 4) wait_flag(g_flag + (6 + ps) * 128 + 8 * r + 2 * lane + kh, target);
                warp_arrive(BAR(B_HRDY + ps));
                PROFH(10 + ps);
            }
        } else {
            if (lane == 0) {
#pragma unroll 1
                for (int k = 0; k < 8; k++) {
                    mbar_wait(BAR(B_PUB + k), 0);
                    fence_gpu();
                    st_relaxed(g_flag + k * 128 + b, target);
                    if (k >= 3 && k <= 5) PROFH1(k - 3);
                }
            }
        }
    }
}

typedef CUresult (*EncodeFn)(CUtensorMap*, CUtensorMapDataType, cuuint32_t, void*, const cuuint64_t*, const cuuint64_t*, const cuuint32_t*,
                             const cuuint32_t*, CUtensorMapInterleave, CUtensorMapSwizzle, CUtensorMapL2promotion, CUtensorMapFloatOOBfill);

static void make_map(EncodeFn fn, CUtensorMap* m, const void* ptr, uint64_t d0, uint64_t d1, uint64_t d2, uint64_t s1, uint64_t s2,
                     uint32_t b0, uint32_t b1, uint32_t b2, CUtensorMapSwizzle sw) {
    cuuint64_t dims[3] = {d0, d1, d2}, strides[2] = {s1, s2};
    cuuint32_t box[3] = {b0, b1, b2}, es[3] = {1, 1, 1};
    CUresult rc = fn(m, CU_TENSOR_MAP_DATA_TYPE_BFLOAT16, 3, (void*)ptr, dims, strides, box, es, CU_TENSOR_MAP_INTERLEAVE_NONE, sw,
                     CU_TENSOR_MAP_L2_PROMOTION_L2_128B, CU_TENSOR_MAP_FLOAT_OOB_FILL_NONE);
    (void)rc;
}

extern "C" void kernel_launch(void* const* d_in, const int* in_sizes, int n_in, void* d_out, int out_size) {
    (void)in_sizes; (void)n_in; (void)out_size;
    static EncodeFn fn = nullptr;
    if (!fn) {
        cudaDriverEntryPointQueryResult st;
        cudaGetDriverEntryPoint("cuTensorMapEncodeTiled", (void**)&fn, cudaEnableDefault, &st);
        cudaFuncSetAttribute(fused_block_kernel, cudaFuncAttributeMaxDynamicSharedMemorySize, SMEM_BYTES);
    }
    Params p;
    p.x = (const bf16*)d_in[0];
    const bf16* wqkv = (const bf16*)d_in[1];
    p.wqkv = wqkv;
    p.wop = (const bf16*)d_in[2];
    p.wg = (const bf16*)d_in[4];
    p.wu = (const bf16*)d_in[5];
    p.wd = (const bf16*)d_in[6];
    p.c = (const bf16*)d_in[7];
    p.wmod = (const bf16*)d_in[8];
    p.out = (bf16*)d_out;
    p.zero = 0;
    make_map(fn, &p.wm, p.wmod, 2688, 448, 1, 5376, 5376 * 448, 16, 224, 1, CU_TENSOR_MAP_SWIZZLE_NONE);
    make_map(fn, &p.xm, p.x, 448, 2048, 1, 896, 896 * 2048, 64, 128, 1, CU_TENSOR_MAP_SWIZZLE_128B);
    make_map(fn, &p.qkv, wqkv, 1344, 448, 1, 2688, 2688 * 448, 64, 224, 1, CU_TENSOR_MAP_SWIZZLE_128B);
    make_map(fn, &p.wo, p.wop, 448, 448, 1, 896, 896 * 448, 64, 224, 1, CU_TENSOR_MAP_SWIZZLE_128B);
    make_map(fn, &p.ga, p.wg, 64, 448, 28, 3584, 128, 64, 32, 2, CU_TENSOR_MAP_SWIZZLE_128B);
    make_map(fn, &p.ua, p.wu, 64, 448, 28, 3584, 128, 64, 32, 2, CU_TENSOR_MAP_SWIZZLE_128B);
    make_map(fn, &p.gb, p.wg, 32, 448, 56, 3584, 64, 32, 32, 3, CU_TENSOR_MAP_SWIZZLE_64B);
    make_map(fn, &p.ub, p.wu, 32, 448, 56, 3584, 64, 32, 32, 3, CU_TENSOR_MAP_SWIZZLE_64B);
    make_map(fn, &p.dn, p.wd, 112, 4, 1792, 224, 896, 64, 1, 32, CU_TENSOR_MAP_SWIZZLE_128B);
    fused_block_kernel<<<GRID, 384, SMEM_BYTES>>>(p);
}
```

```cpp
#include <cuda_runtime.h>
#include <cuda_bf16.h>
#include <cuda.h>
#include <stdint.h>

typedef __nv_bfloat16 bf16;

template<int TB> __device__ __forceinline__ void wgmma_rs_56(float* d, uint32_t a0, uint32_t a1, uint32_t a2, uint32_t a3, uint64_t db, int sd) {
  asm volatile("{\n.reg .pred p;\nsetp.ne.b32 p, %33, 0;\n"
    "wgmma.mma_async.sync.aligned.m64n56k16.f32.bf16.bf16 {%0,%1,%2,%3,%4,%5,%6,%7,%8,%9,%10,%11,%12,%13,%14,%15,%16,%17,%18,%19,%20,%21,%22,%23,%24,%25,%26,%27}, {%28,%29,%30,%31}, %32, p, 1, 1, %34;\n}\n"
    : "+f"(d[0]),"+f"(d[1]),"+f"(d[2]),"+f"(d[3]),"+f"(d[4]),"+f"(d[5]),"+f"(d[6]),"+f"(d[7]),"+f"(d[8]),"+f"(d[9]),"+f"(d[10]),"+f"(d[11]),"+f"(d[12]),"+f"(d[13]),"+f"(d[14]),"+f"(d[15]),"+f"(d[16]),"+f"(d[17]),"+f"(d[18]),"+f"(d[19]),"+f"(d[20]),"+f"(d[21]),"+f"(d[22]),"+f"(d[23]),"+f"(d[24]),"+f"(d[25]),"+f"(d[26]),"+f"(d[27])
    : "r"(a0), "r"(a1), "r"(a2), "r"(a3), "l"(db), "r"(sd), "n"(TB));
}
template<int TB> __device__ __forceinline__ void wgmma_ss_56(float* d, uint64_t da, uint64_t db, int sd) {
  asm volatile("{\n.reg .pred p;\nsetp.ne.b32 p, %30, 0;\n"
    "wgmma.mma_async.sync.aligned.m64n56k16.f32.bf16.bf16 {%0,%1,%2,%3,%4,%5,%6,%7,%8,%9,%10,%11,%12,%13,%14,%15,%16,%17,%18,%19,%20,%21,%22,%23,%24,%25,%26,%27}, %28, %29, p, 1, 1, 0, %31;\n}\n"
    : "+f"(d[0]),"+f"(d[1]),"+f"(d[2]),"+f"(d[3]),"+f"(d[4]),"+f"(d[5]),"+f"(d[6]),"+f"(d[7]),"+f"(d[8]),"+f"(d[9]),"+f"(d[10]),"+f"(d[11]),"+f"(d[12]),"+f"(d[13]),"+f"(d[14]),"+f"(d[15]),"+f"(d[16]),"+f"(d[17]),"+f"(d[18]),"+f"(d[19]),"+f"(d[20]),"+f"(d[21]),"+f"(d[22]),"+f"(d[23]),"+f"(d[24]),"+f"(d[25]),"+f"(d[26]),"+f"(d[27])
    : "l"(da), "l"(db), "r"(sd), "n"(TB));
}
template<int TB> __device__ __forceinline__ void wgmma_rs_256(float* d, uint32_t a0, uint32_t a1, uint32_t a2, uint32_t a3, uint64_t db, int sd) {
  asm volatile("{\n.reg .pred p;\nsetp.ne.b32 p, %133, 0;\n"
    "wgmma.mma_async.sync.aligned.m64n256k16.f32.bf16.bf16 {%0,%1,%2,%3,%4,%5,%6,%7,%8,%9,%10,%11,%12,%13,%14,%15,%16,%17,%18,%19,%20,%21,%22,%23,%24,%25,%26,%27,%28,%29,%30,%31,%32,%33,%34,%35,%36,%37,%38,%39,%40,%41,%42,%43,%44,%45,%46,%47,%48,%49,%50,%51,%52,%53,%54,%55,%56,%57,%58,%59,%60,%61,%62,%63,%64,%65,%66,%67,%68,%69,%70,%71,%72,%73,%74,%75,%76,%77,%78,%79,%80,%81,%82,%83,%84,%85,%86,%87,%88,%89,%90,%91,%92,%93,%94,%95,%96,%97,%98,%99,%100,%101,%102,%103,%104,%105,%106,%107,%108,%109,%110,%111,%112,%113,%114,%115,%116,%117,%118,%119,%120,%121,%122,%123,%124,%125,%126,%127}, {%128,%129,%130,%131}, %132, p, 1, 1, %134;\n}\n"
    : "+f"(d[0]),"+f"(d[1]),"+f"(d[2]),"+f"(d[3]),"+f"(d[4]),"+f"(d[5]),"+f"(d[6]),"+f"(d[7]),"+f"(d[8]),"+f"(d[9]),"+f"(d[10]),"+f"(d[11]),"+f"(d[12]),"+f"(d[13]),"+f"(d[14]),"+f"(d[15]),"+f"(d[16]),"+f"(d[17]),"+f"(d[18]),"+f"(d[19]),"+f"(d[20]),"+f"(d[21]),"+f"(d[22]),"+f"(d[23]),"+f"(d[24]),"+f"(d[25]),"+f"(d[26]),"+f"(d[27]),"+f"(d[28]),"+f"(d[29]),"+f"(d[30]),"+f"(d[31]),"+f"(d[32]),"+f"(d[33]),"+f"(d[34]),"+f"(d[35]),"+f"(d[36]),"+f"(d[37]),"+f"(d[38]),"+f"(d[39]),"+f"(d[40]),"+f"(d[41]),"+f"(d[42]),"+f"(d[43]),"+f"(d[44]),"+f"(d[45]),"+f"(d[46]),"+f"(d[47]),"+f"(d[48]),"+f"(d[49]),"+f"(d[50]),"+f"(d[51]),"+f"(d[52]),"+f"(d[53]),"+f"(d[54]),"+f"(d[55]),"+f"(d[56]),"+f"(d[57]),"+f"(d[58]),"+f"(d[59]),"+f"(d[60]),"+f"(d[61]),"+f"(d[62]),"+f"(d[63]),"+f"(d[64]),"+f"(d[65]),"+f"(d[66]),"+f"(d[67]),"+f"(d[68]),"+f"(d[69]),"+f"(d[70]),"+f"(d[71]),"+f"(d[72]),"+f"(d[73]),"+f"(d[74]),"+f"(d[75]),"+f"(d[76]),"+f"(d[77]),"+f"(d[78]),"+f"(d[79]),"+f"(d[80]),"+f"(d[81]),"+f"(d[82]),"+f"(d[83]),"+f"(d[84]),"+f"(d[85]),"+f"(d[86]),"+f"(d[87]),"+f"(d[88]),"+f"(d[89]),"+f"(d[90]),"+f"(d[91]),"+f"(d[92]),"+f"(d[93]),"+f"(d[94]),"+f"(d[95]),"+f"(d[96]),"+f"(d[97]),"+f"(d[98]),"+f"(d[99]),"+f"(d[100]),"+f"(d[101]),"+f"(d[102]),"+f"(d[103]),"+f"(d[104]),"+f"(d[105]),"+f"(d[106]),"+f"(d[107]),"+f"(d[108]),"+f"(d[109]),"+f"(d[110]),"+f"(d[111]),"+f"(d[112]),"+f"(d[113]),"+f"(d[114]),"+f"(d[115]),"+f"(d[116]),"+f"(d[117]),"+f"(d[118]),"+f"(d[119]),"+f"(d[120]),"+f"(d[121]),"+f"(d[122]),"+f"(d[123]),"+f"(d[124]),"+f"(d[125]),"+f"(d[126]),"+f"(d[127])
    : "r"(a0), "r"(a1), "r"(a2), "r"(a3), "l"(db), "r"(sd), "n"(TB));
}
template<int TB> __device__ __forceinline__ void wgmma_ss_192(float* d, uint64_t da, uint64_t db, int sd) {
  asm volatile("{\n.reg .pred p;\nsetp.ne.b32 p, %98, 0;\n"
    "wgmma.mma_async.sync.aligned.m64n192k16.f32.bf16.bf16 {%0,%1,%2,%3,%4,%5,%6,%7,%8,%9,%10,%11,%12,%13,%14,%15,%16,%17,%18,%19,%20,%21,%22,%23,%24,%25,%26,%27,%28,%29,%30,%31,%32,%33,%34,%35,%36,%37,%38,%39,%40,%41,%42,%43,%44,%45,%46,%47,%48,%49,%50,%51,%52,%53,%54,%55,%56,%57,%58,%59,%60,%61,%62,%63,%64,%65,%66,%67,%68,%69,%70,%71,%72,%73,%74,%75,%76,%77,%78,%79,%80,%81,%82,%83,%84,%85,%86,%87,%88,%89,%90,%91,%92,%93,%94,%95}, %96, %97, p, 1, 1, 0, %99;\n}\n"
    : "+f"(d[0]),"+f"(d[1]),"+f"(d[2]),"+f"(d[3]),"+f"(d[4]),"+f"(d[5]),"+f"(d[6]),"+f"(d[7]),"+f"(d[8]),"+f"(d[9]),"+f"(d[10]),"+f"(d[11]),"+f"(d[12]),"+f"(d[13]),"+f"(d[14]),"+f"(d[15]),"+f"(d[16]),"+f"(d[17]),"+f"(d[18]),"+f"(d[19]),"+f"(d[20]),"+f"(d[21]),"+f"(d[22]),"+f"(d[23]),"+f"(d[24]),"+f"(d[25]),"+f"(d[26]),"+f"(d[27]),"+f"(d[28]),"+f"(d[29]),"+f"(d[30]),"+f"(d[31]),"+f"(d[32]),"+f"(d[33]),"+f"(d[34]),"+f"(d[35]),"+f"(d[36]),"+f"(d[37]),"+f"(d[38]),"+f"(d[39]),"+f"(d[40]),"+f"(d[41]),"+f"(d[42]),"+f"(d[43]),"+f"(d[44]),"+f"(d[45]),"+f"(d[46]),"+f"(d[47]),"+f"(d[48]),"+f"(d[49]),"+f"(d[50]),"+f"(d[51]),"+f"(d[52]),"+f"(d[53]),"+f"(d[54]),"+f"(d[55]),"+f"(d[56]),"+f"(d[57]),"+f"(d[58]),"+f"(d[59]),"+f"(d[60]),"+f"(d[61]),"+f"(d[62]),"+f"(d[63]),"+f"(d[64]),"+f"(d[65]),"+f"(d[66]),"+f"(d[67]),"+f"(d[68]),"+f"(d[69]),"+f"(d[70]),"+f"(d[71]),"+f"(d[72]),"+f"(d[73]),"+f"(d[74]),"+f"(d[75]),"+f"(d[76]),"+f"(d[77]),"+f"(d[78]),"+f"(d[79]),"+f"(d[80]),"+f"(d[81]),"+f"(d[82]),"+f"(d[83]),"+f"(d[84]),"+f"(d[85]),"+f"(d[86]),"+f"(d[87]),"+f"(d[88]),"+f"(d[89]),"+f"(d[90]),"+f"(d[91]),"+f"(d[92]),"+f"(d[93]),"+f"(d[94]),"+f"(d[95])
    : "l"(da), "l"(db), "r"(sd), "n"(TB));
}
template<int TB> __device__ __forceinline__ void wgmma_ss_112(float* d, uint64_t da, uint64_t db, int sd) {
  asm volatile("{\n.reg .pred p;\nsetp.ne.b32 p, %58, 0;\n"
    "wgmma.mma_async.sync.aligned.m64n112k16.f32.bf16.bf16 {%0,%1,%2,%3,%4,%5,%6,%7,%8,%9,%10,%11,%12,%13,%14,%15,%16,%17,%18,%19,%20,%21,%22,%23,%24,%25,%26,%27,%28,%29,%30,%31,%32,%33,%34,%35,%36,%37,%38,%39,%40,%41,%42,%43,%44,%45,%46,%47,%48,%49,%50,%51,%52,%53,%54,%55}, %56, %57, p, 1, 1, 0, %59;\n}\n"
    : "+f"(d[0]),"+f"(d[1]),"+f"(d[2]),"+f"(d[3]),"+f"(d[4]),"+f"(d[5]),"+f"(d[6]),"+f"(d[7]),"+f"(d[8]),"+f"(d[9]),"+f"(d[10]),"+f"(d[11]),"+f"(d[12]),"+f"(d[13]),"+f"(d[14]),"+f"(d[15]),"+f"(d[16]),"+f"(d[17]),"+f"(d[18]),"+f"(d[19]),"+f"(d[20]),"+f"(d[21]),"+f"(d[22]),"+f"(d[23]),"+f"(d[24]),"+f"(d[25]),"+f"(d[26]),"+f"(d[27]),"+f"(d[28]),"+f"(d[29]),"+f"(d[30]),"+f"(d[31]),"+f"(d[32]),"+f"(d[33]),"+f"(d[34]),"+f"(d[35]),"+f"(d[36]),"+f"(d[37]),"+f"(d[38]),"+f"(d[39]),"+f"(d[40]),"+f"(d[41]),"+f"(d[42]),"+f"(d[43]),"+f"(d[44]),"+f"(d[45]),"+f"(d[46]),"+f"(d[47]),"+f"(d[48]),"+f"(d[49]),"+f"(d[50]),"+f"(d[51]),"+f"(d[52]),"+f"(d[53]),"+f"(d[54]),"+f"(d[55])
    : "l"(da), "l"(db), "r"(sd), "n"(TB));
}
template<int TB> __device__ __forceinline__ void wgmma_rs_112(float* d, uint32_t a0, uint32_t a1, uint32_t a2, uint32_t a3, uint64_t db, int sd) {
  asm volatile("{\n.reg .pred p;\nsetp.ne.b32 p, %61, 0;\n"
    "wgmma.mma_async.sync.aligned.m64n112k16.f32.bf16.bf16 {%0,%1,%2,%3,%4,%5,%6,%7,%8,%9,%10,%11,%12,%13,%14,%15,%16,%17,%18,%19,%20,%21,%22,%23,%24,%25,%26,%27,%28,%29,%30,%31,%32,%33,%34,%35,%36,%37,%38,%39,%40,%41,%42,%43,%44,%45,%46,%47,%48,%49,%50,%51,%52,%53,%54,%55}, {%56,%57,%58,%59}, %60, p, 1, 1, %62;\n}\n"
    : "+f"(d[0]),"+f"(d[1]),"+f"(d[2]),"+f"(d[3]),"+f"(d[4]),"+f"(d[5]),"+f"(d[6]),"+f"(d[7]),"+f"(d[8]),"+f"(d[9]),"+f"(d[10]),"+f"(d[11]),"+f"(d[12]),"+f"(d[13]),"+f"(d[14]),"+f"(d[15]),"+f"(d[16]),"+f"(d[17]),"+f"(d[18]),"+f"(d[19]),"+f"(d[20]),"+f"(d[21]),"+f"(d[22]),"+f"(d[23]),"+f"(d[24]),"+f"(d[25]),"+f"(d[26]),"+f"(d[27]),"+f"(d[28]),"+f"(d[29]),"+f"(d[30]),"+f"(d[31]),"+f"(d[32]),"+f"(d[33]),"+f"(d[34]),"+f"(d[35]),"+f"(d[36]),"+f"(d[37]),"+f"(d[38]),"+f"(d[39]),"+f"(d[40]),"+f"(d[41]),"+f"(d[42]),"+f"(d[43]),"+f"(d[44]),"+f"(d[45]),"+f"(d[46]),"+f"(d[47]),"+f"(d[48]),"+f"(d[49]),"+f"(d[50]),"+f"(d[51]),"+f"(d[52]),"+f"(d[53]),"+f"(d[54]),"+f"(d[55])
    : "r"(a0), "r"(a1), "r"(a2), "r"(a3), "l"(db), "r"(sd), "n"(TB));
}

constexpr int DM = 448;
constexpr int NCTA = 128;
#define MAPPING 1
#define GRID 132
#define PINGPONG 0
#define NPOLL 4
#define POLL_GAP 150
#define ALLATONCE 0
#define MAP_S 4
constexpr int SPIN_LIMIT = 1 << 22;

constexpr uint32_t OFF_X = 0, OFF_Y = 114688, OFF_MISC = 229376, SMEM_BYTES = 232448;
constexpr uint32_t Y_VR = 0, Y_K = 28672, Y_KOWN = 57344, Y_VOWN = 71680, Y_Q = 86016;
constexpr uint32_t HALF = 57344;
constexpr uint32_t M_BAR = OFF_MISC;
constexpr uint32_t M_ST = OFF_MISC + 512;
constexpr uint32_t M_G = OFF_MISC + 2304;
constexpr uint32_t M_EPOCH = OFF_MISC + 3040;
enum { B_XFULL = 0, B_FULLK = 7, B_FULLV = 8, B_FULLQ, B_KRFULL, B_VRFULL, B_WOFULL, B_XCH, B_FULL = 16, B_MOD1 = 28, B_MOD2, B_WMFULL,
       B_EMPTY = 32, B_XFREE = B_EMPTY + 12, B_GEMV, B_PEER, B_DONE,
       B_PUB = 48,
       B_WMFREE = 56, B_HRDY, B_GFULL = B_HRDY + 2 };
constexpr uint32_t X_STAT = 49152;

__device__ uint32_t g_ticket;
__device__ __align__(128) uint32_t g_mod[8 * 6 * DM];
__device__ __align__(128) uint32_t g_flag[8 * 16 * 8];
__device__ __align__(128) uint32_t g_kv[17 * 8 * 2 * 3584];
__device__ __align__(128) uint32_t g_ox[2 * 34 * 14336];
#define g_o g_ox
#define g_x1 (g_ox + 34 * 14336)
__device__ __align__(128) float2 g_st[34 * 8 * 64];
__device__ __align__(128) uint32_t g_h2[17 * 224 * 512];
#define PROFH(id)
#define PROFH1(id)
#define PROFC(id)

struct alignas(64) Params {
    CUtensorMap wm, xm, qkv, wo, ga, ua, gb, ub, dn;
    const bf16 *x, *c, *wqkv, *wmod, *wg, *wu, *wd, *wop;
    bf16* out;
    uint32_t zero;
};

__device__ __forceinline__ void mbar_init(uint32_t bar, int cnt) { asm volatile("mbarrier.init.shared::cta.b64 [%0], %1;" ::"r"(bar), "r"(cnt) : "memory"); }
__device__ __forceinline__ void mbar_expect_tx(uint32_t bar, uint32_t bytes) { asm volatile("mbarrier.arrive.expect_tx.shared::cta.b64 _, [%0], %1;" ::"r"(bar), "r"(bytes) : "memory"); }
__device__ __forceinline__ void mbar_arrive(uint32_t bar) { asm volatile("mbarrier.arrive.shared::cta.b64 _, [%0];" ::"r"(bar) : "memory"); }
__device__ __forceinline__ void mbar_wait(uint32_t bar, uint32_t parity) {
    uint32_t ok; int n = 0;
    do {
        asm volatile("{\n.reg .pred p;\nmbarrier.try_wait.parity.shared::cta.b64 p, [%1], %2;\nselp.u32 %0, 1, 0, p;\n}" : "=r"(ok) : "r"(bar), "r"(parity) : "memory");
        if (++n > SPIN_LIMIT) __trap();
    } while (!ok);
}
__device__ __forceinline__ void mbar_wait_cluster(uint32_t bar, uint32_t parity) {
    uint32_t ok; int n = 0;
    do {
        asm volatile("{\n.reg .pred p;\nmbarrier.try_wait.parity.acquire.cluster.shared::cta.b64 p, [%1], %2;\nselp.u32 %0, 1, 0, p;\n}" : "=r"(ok) : "r"(bar), "r"(parity) : "memory");
        if (++n > SPIN_LIMIT) __trap();
    } while (!ok);
}
__device__ __forceinline__ void warp_arrive(uint32_t bar) {
    __syncwarp();
    asm volatile("{\n.reg .pred p;\nelect.sync _|p, 0xffffffff;\n@p mbarrier.arrive.shared::cta.b64 _, [%0];\n}" ::"r"(bar) : "memory");
}
__device__ __forceinline__ int opaque(int v) { return __shfl_sync(~0u, v, 0); }
__device__ __forceinline__ int fresh_tid() { int v; asm volatile("mov.u32 %0, %%tid.x;" : "=r"(v)); return v; }
__device__ __forceinline__ void bar_sync(int id, int n) { asm volatile("bar.sync %0, %1;" ::"r"(id), "r"(n) : "memory"); }
__device__ __forceinline__ void bar_arrive(int id, int n) { asm volatile("bar.arrive %0, %1;" ::"r"(id), "r"(n) : "memory"); }
__device__ __forceinline__ void fence_async_smem() { asm volatile("fence.proxy.async.shared::cta;" ::: "memory"); }
__device__ __forceinline__ void fence_async_global() { asm volatile("fence.proxy.async.global;" ::: "memory"); }
__device__ __forceinline__ void fence_gpu() { asm volatile("fence.release.gpu;" ::: "memory"); }
__device__ __forceinline__ void tma3(uint32_t dst, const CUtensorMap* m, int c0, int c1, int c2, uint32_t bar) {
    asm volatile("cp.async.bulk.tensor.3d.shared::cluster.global.mbarrier::complete_tx::bytes [%0], [%1, {%3, %4, %5}], [%2];"
                 ::"r"(dst), "l"(m), "r"(bar), "r"(c0), "r"(c1), "r"(c2) : "memory");
}
__device__ __forceinline__ void bulk_load(uint32_t dst, const void* src, uint32_t bytes, uint32_t bar) {
    asm volatile("cp.async.bulk.shared::cluster.global.mbarrier::complete_tx::bytes [%0], [%1], %2, [%3];" ::"r"(dst), "l"(src), "r"(bytes), "r"(bar) : "memory");
}
__device__ __forceinline__ void expect_e(uint32_t bar, uint32_t bytes) {
    asm volatile("{\n.reg .pred p;\nelect.sync _|p, 0xffffffff;\n@p mbarrier.arrive.expect_tx.shared::cta.b64 _, [%0], %1;\n}" ::"r"(bar), "r"(bytes) : "memory");
}
__device__ __forceinline__ void tma3_e(uint32_t dst, const CUtensorMap* m, int c0, int c1, int c2, uint32_t bar) {
    asm volatile("{\n.reg .pred p;\nelect.sync _|p, 0xffffffff;\n@p cp.async.bulk.tensor.3d.shared::cluster.global.mbarrier::complete_tx::bytes [%0], [%1, {%3, %4, %5}], [%2];\n}"
                 ::"r"(dst), "l"(m), "r"(bar), "r"(c0), "r"(c1), "r"(c2) : "memory");
}
__device__ __forceinline__ void bulk_e(uint32_t dst, const void* src, uint32_t bytes, uint32_t bar) {
    asm volatile("{\n.reg .pred p;\nelect.sync _|p, 0xffffffff;\n@p cp.async.bulk.shared::cluster.global.mbarrier::complete_tx::bytes [%0], [%1], %2, [%3];\n}"
                 ::"r"(dst), "l"(src), "r"(bytes), "r"(bar) : "memory");
}
__device__ __forceinline__ void init_e(uint32_t bar, int cnt) {
    asm volatile("{\n.reg .pred p;\nelect.sync _|p, 0xffffffff;\n@p mbarrier.init.shared::cta.b64 [%0], %1;\n}" ::"r"(bar), "r"(cnt) : "memory");
}
__device__ __forceinline__ void l2_prefetch(const void* src, uint32_t bytes) { asm volatile("cp.async.bulk.prefetch.L2.global [%0], %1;" ::"l"(src), "r"(bytes) : "memory"); }
__device__ __forceinline__ uint32_t ld_relaxed(const uint32_t* p) { uint32_t v; asm volatile("ld.relaxed.gpu.global.u32 %0, [%1];" : "=r"(v) : "l"(p) : "memory"); return v; }
__device__ __forceinline__ void st_relaxed(uint32_t* p, uint32_t v) { asm volatile("st.relaxed.gpu.global.u32 [%0], %1;" ::"l"(p), "r"(v) : "memory"); }
__device__ __forceinline__ uint4 ld_relaxed4(const uint4* p) { uint4 v; asm volatile("ld.relaxed.gpu.global.v4.u32 {%0,%1,%2,%3}, [%4];" : "=r"(v.x), "=r"(v.y), "=r"(v.z), "=r"(v.w) : "l"(p) : "memory"); return v; }
__device__ __forceinline__ void st_relaxed4(uint4* p, uint4 v) { asm volatile("st.relaxed.gpu.global.v4.u32 [%0], {%1,%2,%3,%4};" ::"l"(p), "r"(v.x), "r"(v.y), "r"(v.z), "r"(v.w) : "memory"); }
__device__ __forceinline__ uint4 ldg_nc4(const void* p) { uint4 v; asm volatile("ld.global.nc.L1::no_allocate.v4.u32 {%0,%1,%2,%3}, [%4];" : "=r"(v.x), "=r"(v.y), "=r"(v.z), "=r"(v.w) : "l"(p)); return v; }
__device__ __forceinline__ uint32_t ldg_nc(const void* p) { uint32_t v; asm volatile("ld.global.nc.u32 %0, [%1];" : "=r"(v) : "l"(p)); return v; }
__device__ __forceinline__ uint32_t ld_acquire(const uint32_t* p) { uint32_t v; asm volatile("ld.acquire.gpu.global.u32 %0, [%1];" : "=r"(v) : "l"(p) : "memory"); return v; }
__device__ __forceinline__ uint4 lds4(uint32_t a) { uint4 v; asm volatile("ld.shared.v4.u32 {%0,%1,%2,%3}, [%4];" : "=r"(v.x), "=r"(v.y), "=r"(v.z), "=r"(v.w) : "r"(a) : "memory"); return v; }
__device__ __forceinline__ float2 lds2f(uint32_t a) { float2 v; asm volatile("ld.shared.v2.f32 {%0,%1}, [%2];" : "=f"(v.x), "=f"(v.y) : "r"(a) : "memory"); return v; }
__device__ __forceinline__ uint32_t lds1(uint32_t a) { uint32_t v; asm volatile("ld.shared.u32 %0, [%1];" : "=r"(v) : "r"(a) : "memory"); return v; }
__device__ __forceinline__ void sts4(uint32_t a, uint4 v) { asm volatile("st.shared.v4.u32 [%0], {%1,%2,%3,%4};" ::"r"(a), "r"(v.x), "r"(v.y), "r"(v.z), "r"(v.w) : "memory"); }
__device__ __forceinline__ void sts2(uint32_t a, uint32_t x, uint32_t y) { asm volatile("st.shared.v2.u32 [%0], {%1,%2};" ::"r"(a), "r"(x), "r"(y) : "memory"); }
__device__ __forceinline__ void sts1(uint32_t a, uint32_t v) { asm volatile("st.shared.u32 [%0], %1;" ::"r"(a), "r"(v) : "memory"); }
__device__ __forceinline__ void stsm4(uint32_t a, uint32_t r0, uint32_t r1, uint32_t r2, uint32_t r3) {
    asm volatile("stmatrix.sync.aligned.m8n8.x4.shared.b16 [%0], {%1,%2,%3,%4};" ::"r"(a), "r"(r0), "r"(r1), "r"(r2), "r"(r3));
}
__device__ __forceinline__ uint32_t pack2(float lo, float hi) { uint32_t r; asm("cvt.rn.bf16x2.f32 %0, %1, %2;" : "=r"(r) : "f"(hi), "f"(lo)); return r; }
__device__ __forceinline__ uint32_t pack2_relu(float lo, float hi) { uint32_t r; asm("cvt.rn.relu.bf16x2.f32 %0, %1, %2;" : "=r"(r) : "f"(hi), "f"(lo)); return r; }
__device__ __forceinline__ uint32_t hfma2(uint32_t a, uint32_t b, uint32_t c) { uint32_t r; asm("fma.rn.bf16x2 %0, %1, %2, %3;" : "=r"(r) : "r"(a), "r"(b), "r"(c)); return r; }
__device__ __forceinline__ uint32_t hmul2(uint32_t a, uint32_t b) { uint32_t r; asm("mul.rn.bf16x2 %0, %1, %2;" : "=r"(r) : "r"(a), "r"(b)); return r; }
__device__ __forceinline__ float bf_lo(uint32_t v) { return __uint_as_float(v << 16); }
__device__ __forceinline__ float bf_hi(uint32_t v) { return __uint_as_float(v & 0xFFFF0000u); }
__device__ __forceinline__ float bf_round(float v) { return bf_lo(pack2(v, 0.f)); }
__device__ __forceinline__ float ex2(float x) { float r; asm("ex2.approx.ftz.f32 %0, %1;" : "=f"(r) : "f"(x)); return r; }
__device__ __forceinline__ void mma16816(float* d, uint32_t a0, uint32_t a1, uint32_t a2, uint32_t a3, uint32_t b0, uint32_t b1) {
    asm("mma.sync.aligned.m16n8k16.row.col.f32.bf16.bf16.f32 {%0,%1,%2,%3}, {%4,%5,%6,%7}, {%8,%9}, {%0,%1,%2,%3};"
        : "+f"(d[0]), "+f"(d[1]), "+f"(d[2]), "+f"(d[3]) : "r"(a0), "r"(a1), "r"(a2), "r"(a3), "r"(b0), "r"(b1));
}
__device__ __forceinline__ void mma16816_first(float* d, uint32_t a0, uint32_t a1, uint32_t a2, uint32_t a3, uint32_t b0, uint32_t b1) {
    asm volatile("mma.sync.aligned.m16n8k16.row.col.f32.bf16.bf16.f32 {%0,%1,%2,%3}, {%4,%5,%6,%7}, {%8,%9}, {%10,%10,%10,%10};"
        : "=f"(d[0]), "=f"(d[1]), "=f"(d[2]), "=f"(d[3]) : "r"(a0), "r"(a1), "r"(a2), "r"(a3), "r"(b0), "r"(b1), "f"(0.f));
}
__device__ __forceinline__ void mma16816_v(float* d, uint32_t a0, uint32_t a1, uint32_t a2, uint32_t a3, uint32_t b0, uint32_t b1) {
    asm volatile("mma.sync.aligned.m16n8k16.row.col.f32.bf16.bf16.f32 {%0,%1,%2,%3}, {%4,%5,%6,%7}, {%8,%9}, {%0,%1,%2,%3};"
        : "+f"(d[0]), "+f"(d[1]), "+f"(d[2]), "+f"(d[3]) : "r"(a0), "r"(a1), "r"(a2), "r"(a3), "r"(b0), "r"(b1));
}
__device__ __forceinline__ void mma1688(float* d, uint32_t a0, uint32_t a1, uint32_t b0) {
    asm("mma.sync.aligned.m16n8k8.row.col.f32.bf16.bf16.f32 {%0,%1,%2,%3}, {%4,%5}, {%6}, {%0,%1,%2,%3};"
        : "+f"(d[0]), "+f"(d[1]), "+f"(d[2]), "+f"(d[3]) : "r"(a0), "r"(a1), "r"(b0));
}
__device__ __forceinline__ void ldsm4(uint32_t a, uint32_t* r) {
    asm volatile("ldmatrix.sync.aligned.m8n8.x4.shared.b16 {%0,%1,%2,%3}, [%4];" : "=r"(r[0]), "=r"(r[1]), "=r"(r[2]), "=r"(r[3]) : "r"(a));
}
__device__ __forceinline__ void ldsm4t(uint32_t a, uint32_t* r) {
    asm volatile("ldmatrix.sync.aligned.m8n8.x4.trans.shared.b16 {%0,%1,%2,%3}, [%4];" : "=r"(r[0]), "=r"(r[1]), "=r"(r[2]), "=r"(r[3]) : "r"(a));
}
__device__ __forceinline__ float rcp(float x) { float r; asm("rcp.approx.ftz.f32 %0, %1;" : "=f"(r) : "f"(x)); return r; }
__device__ __forceinline__ uint2 ld_relaxed2(const void* p) { uint2 v; asm volatile("ld.relaxed.gpu.global.v2.u32 {%0,%1}, [%2];" : "=r"(v.x), "=r"(v.y) : "l"(p) : "memory"); return v; }
__device__ __forceinline__ void st_relaxed2(void* p, uint32_t x, uint32_t y) { asm volatile("st.relaxed.gpu.global.v2.u32 [%0], {%1,%2};" ::"l"(p), "r"(max(x, 1u)), "r"(max(y, 1u)) : "memory"); }
__device__ __forceinline__ constexpr uint64_t dconst(uint32_t lbo, uint32_t sbo, uint32_t swz) {
    return ((uint64_t)(lbo >> 4) << 16) | ((uint64_t)(sbo >> 4) << 32) | ((uint64_t)swz << 62);
}
__device__ __forceinline__ uint64_t mkdesc(uint32_t addr, uint64_t c) { return c | (uint64_t)((addr & 0x3FFFF) >> 4); }
#define WG_FENCE() asm volatile("wgmma.fence.sync.aligned;" ::: "memory")
#define WG_COMMIT() asm volatile("wgmma.commit_group.sync.aligned;" ::: "memory")
#define WG_WAIT(n) asm volatile("wgmma.wait_group.sync.aligned %0;" ::"n"(n) : "memory")
template <int N> __device__ __forceinline__ void reg_fence(float* d) {
#pragma unroll
    for (int i = 0; i < N; i++) asm volatile("" : "+f"(d[i])::"memory");
}
template <int N> __device__ __forceinline__ void reg_def(float* d) {
#pragma unroll
    for (int i = 0; i < N; i++) asm volatile("" : "=f"(d[i]));
}
template <int N> __device__ __forceinline__ void reg_def(uint32_t* d) {
#pragma unroll
    for (int i = 0; i < N; i++) asm volatile("" : "=r"(d[i]));
}
__device__ __forceinline__ bool is_unset(uint4 v) { return min(min(v.x, v.y), min(v.z, v.w)) == 0u; }
__device__ __forceinline__ uint4 nz4(uint32_t a, uint32_t b, uint32_t c, uint32_t d) { return make_uint4(max(a, 1u), max(b, 1u), max(c, 1u), max(d, 1u)); }
__device__ __forceinline__ void wait_flag(const uint32_t* p, uint32_t target) {
    int n = 0;
    while ((int)(ld_relaxed(p) - target) < 0) { if (++n > SPIN_LIMIT) __trap(); }
    asm volatile("fence.acquire.gpu;" ::: "memory");
}
__device__ __forceinline__ float silu_bf(uint32_t cbits) {
    const float c = __uint_as_float(cbits << 16);
    return bf_round(__fdividef(c, 1.f + fminf(ex2(-1.4426950408889634f * c), 1e30f)));
}
__device__ __forceinline__ void gemv_part(uint32_t wmbuf, int npanel, int wp, int lane) {
    const uint32_t wa = wmbuf + wp * 512 + (8 * (lane >> 4) + (lane & 7)) * 32 + ((lane >> 3) & 1) * 16;
    uint2 B[4];
#pragma unroll
    for (int i = 0; i < 4; i++) { const float2 v = lds2f(wmbuf + 28672 + (wp + 8 * i) * 32 + (lane & 3) * 8); B[i] = make_uint2(__float_as_uint(v.x), __float_as_uint(v.y)); }
#pragma unroll 1
    for (int pn = 0; pn < npanel; pn++) {
        float d[4] = {};
        uint32_t A[16];
#pragma unroll
        for (int i = 0; i < 4; i++) ldsm4t(wa + pn * 14336 + (i < 3 || wp < 4 ? i : 0) * 4096, A + 4 * i);
#pragma unroll
        for (int i = 0; i < 4; i++) mma16816(d, A[4 * i], A[4 * i + 1], A[4 * i + 2], A[4 * i + 3], B[i].x, B[i].y);
        if ((lane & 3) == 0) {
            sts1(wmbuf + 29696 + (wp * 32 + pn * 16 + (lane >> 2)) * 4, __float_as_uint(d[0]));
            sts1(wmbuf + 29696 + (wp * 32 + pn * 16 + 8 + (lane >> 2)) * 4, __float_as_uint(d[2]));
        }
    }
}
__device__ __forceinline__ uint32_t slot_off(int l) { return (l < 3 || l > 6 ? l : l == 6 ? 3 : l + 1) * 16384; }
__device__ __forceinline__ void ln_coeffs(float mean, float msq, uint32_t& r2, uint32_t& n2) {
    const float rs = bf_round(rsqrtf(fmaxf(msq - mean * mean, 0.f) + 1e-5f));
    r2 = pack2(rs, rs);
    n2 = pack2(-mean * rs, -mean * rs);
}

__global__ void __cluster_dims__(2, 1, 1) __launch_bounds__(384, 1) fused_block_kernel(const __grid_constant__ Params p) {
    extern __shared__ __align__(1024) unsigned char smem[];
    const uint32_t sb = (uint32_t)__cvta_generic_to_shared(smem);
    const int tid = threadIdx.x, lane = tid & 31, warp = __shfl_sync(~0u, tid >> 5, 0);
    const int m = blockIdx.x >> 1;
#define kh (j & 1)
    int r, nq;
    {
        int g, i;
        if (m < MAP_S) { g = m < 4 ? 15 : 16; i = m & 3; }
        else if (m < MAP_S + 32) { g = (m - MAP_S) & 7; i = (m - MAP_S) >> 3; }
        else if (m < MAP_S + 60) { i = (m - MAP_S - 32) / 7; g = 8 + (m - MAP_S - 32) - 7 * i; }
        else { g = 16; i = m & 3; }
        r = g; nq = i;
    }
    const int j = opaque(2 * nq + (blockIdx.x & 1)), b = 8 * r + j, fs = 4 * kh + nq;
    const uint32_t sc = r == 16;
#define BAR(i) (sb + M_BAR + 8 * (i))
    if (lane == 0 && warp < 9 && warp != 6 && warp != 7) {
        const int i0 = warp == 8 ? 0 : 8 + 8 * warp, cnt = warp == 0 || warp == 8 ? 1 : warp < 3 ? 2 : 8;
#pragma unroll
        for (int k = 0; k < 8; k++) if (i0 + k != B_WMFULL) mbar_init(BAR(i0 + k), cnt);
        asm volatile("fence.mbarrier_init.release.cluster;" ::: "memory");
        fence_async_smem();
    }

    if (warp < 8) {
        const int w = warp >> 2, wi = warp & 3;
#define COORDS const int t = fresh_tid() & 127, lane = t & 31, q = lane & 3, lr = lane >> 2, ra = 64 * w + 16 * wi + lr; \
        const uint32_t lx = (lane >> 4) ^ (lane & 7), mrow = (64 * w + 16 * wi + ((lane >> 3) & 1) * 8 + (lane & 7)) * 128; \
        (void)q; (void)lr; (void)ra; (void)lx; (void)mrow;
        const int sid = 2 * (j & 3) + w;
#define RUN(k) (!sc || sid == (k))
#define WAIT(i, par) mbar_wait(BAR(i), (par) | sc)
        constexpr uint64_t DB128 = dconst(4096, 1024, 1);
        bar_arrive(9, 384);
        bar_sync(0, 384);
        asm volatile("barrier.cluster.arrive.relaxed.aligned;" ::: "memory");
        asm volatile("setmaxnreg.inc.sync.aligned.u32 224;");
        PROFC(0);
        uint32_t xr[16];
        {
            COORDS
            uint32_t h[112];
            if (RUN(0)) {
                float ds[4] = {}, da[2][4] = {}, db[2][4] = {};
                const uint32_t ONE2 = 0x3F803F80u;
                if (kh == 0) { WAIT(B_WMFULL, 0); gemv_part(sb + OFF_Y + HALF, 1, warp, lane); warp_arrive(BAR(B_GEMV)); }
#pragma unroll
                for (int kb = 0; kb < 7; kb++) {
                    WAIT(B_XFULL + kb, 0);
#pragma unroll
                    for (int k4 = 0; k4 < 4; k4++) ldsm4(sb + OFF_X + mrow + kb * 16384 + (((2 * k4) ^ lx) << 4), h + 16 * kb + 4 * k4);
#pragma unroll
                    for (int k4 = 0; k4 < 4; k4++) {
                        const uint32_t* f = h + 16 * kb + 4 * k4;
                        mma16816(ds, f[0], f[1], f[2], f[3], ONE2, ONE2);
                        mma1688(da[0], f[0], f[1], f[0]); mma1688(db[0], f[0], f[1], f[1]);
                        mma1688(da[1], f[2], f[3], f[2]); mma1688(db[1], f[2], f[3], f[3]);
                    }
                }
#pragma unroll
                for (int i = 0; i < 4; i++) {
                    const int ch = 7 * j + 2 * i + (lane >> 4);
                    ldsm4(sb + OFF_X + mrow + (ch >> 3) * 16384 + (((ch ^ lane) & 7) << 4), xr + 4 * i);
                }
                warp_arrive(BAR(B_XFREE));
                PROFC(27);
                float qa = (lr & 1) ? da[0][1] + da[1][1] : da[0][0] + da[1][0];
                float qb = (lr & 1) ? db[0][3] + db[1][3] : db[0][2] + db[1][2];
                const int src = (lane & ~3) | (lr >> 1);
                qa = __shfl_sync(~0u, qa, src);
                qb = __shfl_sync(~0u, qb, src);
                uint32_t ra2, na2, rb2, nb2;
                ln_coeffs(ds[0] * (1.f / DM), qa * (1.f / DM), ra2, na2);
                ln_coeffs(ds[2] * (1.f / DM), qb * (1.f / DM), rb2, nb2);
#pragma unroll
                for (int i = 0; i < 112; i += 2) { h[i] = hfma2(h[i], ra2, na2); h[i + 1] = hfma2(h[i + 1], rb2, nb2); }
                if (kh == 1) { WAIT(B_WMFULL, 0); gemv_part(sb + OFF_Y + HALF, 2, warp, lane); warp_arrive(BAR(B_GEMV)); }
            } else { reg_def<112>(h); reg_def<16>(xr); }
            PROFC(1);
            if (RUN(1)) {
                float ak[28], av[28], aq[28];
                uint32_t kp[14], vp[14];
                const uint64_t bk0 = mkdesc(sb + OFF_Y, DB128) + kh, bv0 = mkdesc(sb + OFF_Y + HALF, DB128) + kh, bq0 = mkdesc(sb + OFF_X, DB128) + kh;
                uint32_t* kvg = g_kv + (size_t)(b * 2) * 3584 + (8 * w + 2 * wi) * 224 + lane;
                WAIT(B_FULLK, 0);
                WAIT(B_MOD1, 0);
                PROFC(2);
                reg_def<28>(ak);
#pragma unroll
                for (int g4 = 0; g4 < 4; g4++) {
#pragma unroll
                    for (int ks = 7 * g4; ks < 7 * g4 + 7; ks++) {
                        const uint4 st = *(const uint4*)(smem + M_ST + ks * 64 + q * 16);
                        h[4 * ks] = hfma2(h[4 * ks], st.x, st.y); h[4 * ks + 1] = hfma2(h[4 * ks + 1], st.x, st.y);
                        h[4 * ks + 2] = hfma2(h[4 * ks + 2], st.z, st.w); h[4 * ks + 3] = hfma2(h[4 * ks + 3], st.z, st.w);
                    }
                    WG_FENCE();
#pragma unroll
                    for (int ks = 7 * g4; ks < 7 * g4 + 7; ks++) wgmma_rs_56<1>(ak, h[4 * ks], h[4 * ks + 1], h[4 * ks + 2], h[4 * ks + 3], bk0 + ks * 128, ks != 0);
                }
                WG_COMMIT();
                PROFC(3);
                WAIT(B_FULLV, 0);
                reg_def<28>(av);
                WG_FENCE();
#pragma unroll
                for (int ks = 0; ks < 8; ks++) wgmma_rs_56<1>(av, h[4 * ks], h[4 * ks + 1], h[4 * ks + 2], h[4 * ks + 3], bv0 + ks * 128, ks != 0);
                WG_COMMIT();
                WG_WAIT(1);
                reg_fence<28>(ak);
#pragma unroll
                for (int g = 0; g < 7; g++) {
                    kp[2 * g] = pack2(ak[4 * g], ak[4 * g + 1]); kp[2 * g + 1] = pack2(ak[4 * g + 2], ak[4 * g + 3]);
                    kvg[g * 32] = kp[2 * g]; kvg[224 + g * 32] = kp[2 * g + 1];
                }
                warp_arrive(BAR(B_PUB));
                PROFC(4);
                WG_FENCE();
#pragma unroll
                for (int ks = 8; ks < 28; ks++) wgmma_rs_56<1>(av, h[4 * ks], h[4 * ks + 1], h[4 * ks + 2], h[4 * ks + 3], bv0 + ks * 128, 1);
                WG_COMMIT();
                WAIT(B_FULLQ, 0);
                reg_def<28>(aq);
                WG_FENCE();
#pragma unroll
                for (int ks = 0; ks < 8; ks++) wgmma_rs_56<1>(aq, h[4 * ks], h[4 * ks + 1], h[4 * ks + 2], h[4 * ks + 3], bq0 + ks * 128, ks != 0);
                WG_COMMIT();
                WG_WAIT(1);
                reg_fence<28>(av);
#pragma unroll
                for (int g = 0; g < 7; g++) {
                    vp[2 * g] = pack2(av[4 * g], av[4 * g + 1]); vp[2 * g + 1] = pack2(av[4 * g + 2], av[4 * g + 3]);
                    kvg[3584 + g * 32] = vp[2 * g]; kvg[3584 + 224 + g * 32] = vp[2 * g + 1];
                }
                warp_arrive(BAR(B_PUB + 1));
                PROFC(5);
                WG_FENCE();
#pragma unroll
                for (int ks = 8; ks < 28; ks++) wgmma_rs_56<1>(aq, h[4 * ks], h[4 * ks + 1], h[4 * ks + 2], h[4 * ks + 3], bq0 + ks * 128, 1);
                WG_COMMIT();
                WAIT(B_PUB + 1, 0);
                const uint32_t ko = sb + OFF_Y + Y_KOWN + (8 * w + 2 * wi) * 896 + lane * 4;
                const uint32_t qo = sb + OFF_Y + Y_Q + (8 * w + 2 * wi) * 1024 + lane * 4;
#pragma unroll
                for (int g = 0; g < 7; g++) {
                    sts1(ko + g * 128, kp[2 * g]); sts1(ko + 896 + g * 128, kp[2 * g + 1]);
                    sts1(ko + (Y_VOWN - Y_KOWN) + g * 128, vp[2 * g]); sts1(ko + (Y_VOWN - Y_KOWN) + 896 + g * 128, vp[2 * g + 1]);
                }
                WG_WAIT(0);
                reg_fence<28>(aq);
                __syncwarp();
                if (lane < 3 && w == 1) mbar_arrive(BAR(B_EMPTY + lane));
#pragma unroll
                for (int g = 0; g < 7; g++) {
                    const uint32_t q0 = pack2(aq[4 * g], aq[4 * g + 1]), q1 = pack2(aq[4 * g + 2], aq[4 * g + 3]);
                    if (g == 3) {
                        sts1(qo + 3 * 128, q < 2 ? q0 : 0u); sts1(qo + 1024 + 3 * 128, q < 2 ? q1 : 0u);
                        sts1(qo + 4 * 128, q < 2 ? 0u : q0); sts1(qo + 1024 + 4 * 128, q < 2 ? 0u : q1);
                    } else {
                        const int ch = g < 3 ? g : g + 1;
                        sts1(qo + ch * 128, q0); sts1(qo + 1024 + ch * 128, q1);
                    }
                }
                if (!sc) bar_sync(3, 256);
            }
        }
        PROFC(6);
        WAIT(B_KRFULL, 0);
        PROFC(7);
        if (RUN(2)) {
#pragma unroll 1
            for (int hf = sc; hf < 2; hf++) {
                COORDS
                float s[136];
                float na = 0.f, nb = 0.f;
                const float CS = 0.18898223650461361f * 1.4426950408889634f;
                const int kg0 = 8 * hf + 2 * wi;
                const int pmin = 16 - 8 * r - 4 * hf - wi;
                const float NEG = __int_as_float(0xFF800000);
                {
                    uint32_t F[8];
                    const uint32_t qa = sb + OFF_Y + Y_Q + (kg0 + ((lane >> 3) & 1)) * 1024 + (4 * w + (lane >> 4)) * 128 + (lane & 7) * 16;
                    ldsm4(qa, F); ldsm4(qa + 256, F + 4);
                    uint32_t ka = sb + OFF_Y + Y_K + kg0 * 896 + (3 * w + (lane >> 3)) * 128 + (lane & 7) * 16;
#pragma unroll
                    for (int g = 0; g < 34; g++) {
                        uint32_t B[4];
                        if (g >= 12 && g % 4 == 0) ka += __float_as_uint(s[4 * (g - 12)]) & p.zero;
                        ldsm4(ka + g * 896, B);
                        mma16816_first(s + 4 * g, F[0], F[1], F[2], F[3], B[0], B[1]);
                        mma16816_v(s + 4 * g, F[4], F[5], F[6], F[7], B[2], B[3]);
                    }
                    const bool c0 = 2 * q > lr, c1 = 2 * q + 1 > lr;
                    if (!c0) { s[0] = NEG; s[6] = NEG; }
                    if (!c1) { s[1] = NEG; s[7] = NEG; }
                    s[2] = NEG; s[3] = NEG;
                    if (c0) { s[128] = NEG; s[134] = NEG; }
                    if (c1) { s[129] = NEG; s[135] = NEG; }
                    s[132] = NEG; s[133] = NEG;
                    float ma = NEG, mb = NEG;
#pragma unroll
                    for (int pp = 0; pp < 17; pp++) {
                        const float* e = s + 8 * pp;
                        const float bias = pp < pmin ? NEG : 0.f;
                        ma = fmaxf(ma, fmaxf(fmaxf(e[0], e[1]), fmaxf(e[4], e[5])) + bias);
                        mb = fmaxf(mb, fmaxf(fmaxf(e[2], e[3]), fmaxf(e[6], e[7])) + bias);
                    }
                    ma = fmaxf(ma, __shfl_xor_sync(~0u, ma, 1)); mb = fmaxf(mb, __shfl_xor_sync(~0u, mb, 1));
                    ma = fmaxf(ma, __shfl_xor_sync(~0u, ma, 2)); mb = fmaxf(mb, __shfl_xor_sync(~0u, mb, 2));
                    na = -ma * CS; nb = -mb * CS;
                }
                PROFC(8 + 3 * hf);
                {
                    if (hf == 0) mbar_wait(BAR(B_VRFULL), 0);
                    float o[16] = {}, rs[4] = {};
                    const uint32_t va = sb + OFF_Y + Y_VR + (kg0 + ((lane >> 3) & 1)) * 896 + (3 * w + (lane >> 4)) * 128 + (lane & 7) * 16;
#pragma unroll
                    for (int pp = 0; pp < 17; pp++) {
                        uint32_t B[8];
                        const uint32_t v = va + pp * 1792 + (pp == 16 || (pp >= 9 && kg0 + 2 * pp >= 32) ? Y_VOWN - 32 * 896 : 0);
                        ldsm4t(v, B); ldsm4t(v + 256, B + 4);
                        float e[8];
#pragma unroll
                        for (int i = 0; i < 8; i++) e[i] = ex2(fmaf(s[8 * pp + i], CS, ((i & 2) ? nb : na) + (pp < pmin ? NEG : 0.f)));
                        const uint32_t p0 = pack2(e[0], e[1]), p1 = pack2(e[2], e[3]), p2 = pack2(e[4], e[5]), p3 = pack2(e[6], e[7]);
                        mma16816(rs, p0, p1, p2, p3, 0x3F803F80u, 0x3F803F80u);
#pragma unroll
                        for (int g = 0; g < 4; g++) mma16816(o + 4 * g, p0, p1, p2, p3, B[2 * g], B[2 * g + 1]);
                    }
                    PROFC(9 + 3 * hf);
                    const float ia = rcp(rs[0]), ib = rcp(rs[2]);
                    uint32_t* og = g_o + (size_t)(2 * r + hf) * 14336 + (7 * j + 3 * w) * 256 + wi * 64 + lane;
#pragma unroll
                    for (int g = 0; g < 4; g++) {
                        if ((g == 3 - 3 * w) ? ((q >> 1) == w) : true) {
                            og[g * 256] = pack2(o[4 * g] * ia, o[4 * g + 1] * ia);
                            og[g * 256 + 32] = pack2(o[4 * g + 2] * ib, o[4 * g + 3] * ib);
                        }
                    }
                    warp_arrive(BAR(B_PUB + 2 + hf));
                    PROFC(10 + 3 * hf);
                }
            }
        }
        uint32_t x1p[14];
        COORDS
        constexpr uint64_t DT = dconst(1024, 128, 0);
        if (RUN(4)) {
            float ac[28];
            const uint64_t ad = mkdesc(sb + (w ? OFF_Y + HALF : OFF_X), DT), bd = mkdesc(sb + OFF_X + HALF, DB128) + kh;
            WAIT(B_WOFULL, 0);
            WAIT(B_MOD2, 0);
            WAIT(B_GFULL + w, 0);
            PROFC(28);
            reg_def<28>(ac);
#pragma unroll 1
            for (int u = 0; u < 4; u++) {
                WG_FENCE();
#pragma unroll
                for (int i = 0; i < 7; i++) wgmma_ss_56<1>(ac, ad + (7 * u + i) * 128, bd + (7 * u + i) * 128, (u | i) != 0);
            }
            WG_COMMIT();
            WG_WAIT(0);
            reg_fence<28>(ac);
            PROFC(14);
            __syncwarp();
            if (lane < 3) mbar_arrive(BAR(B_EMPTY + 3 + lane));
            if (lane < 3 && w == 0) mbar_arrive(BAR(B_EMPTY + lane));
            float s1a = 0.f, s2a = 0.f, s1b = 0.f, s2b = 0.f;
            uint32_t* xo = g_x1 + (size_t)(2 * r + w) * 14336 + 7 * j * 256 + wi * 64 + lane;
#pragma unroll
            for (int g = 0; g < 7; g++) {
                const float2 ga = *(const float2*)(smem + M_G + (8 * g + 2 * q) * 4);
                x1p[2 * g] = pack2(fmaf(ga.x, ac[4 * g], bf_lo(xr[2 * g])), fmaf(ga.y, ac[4 * g + 1], bf_hi(xr[2 * g])));
                x1p[2 * g + 1] = pack2(fmaf(ga.x, ac[4 * g + 2], bf_lo(xr[2 * g + 1])), fmaf(ga.y, ac[4 * g + 3], bf_hi(xr[2 * g + 1])));
                xo[g * 256] = x1p[2 * g]; xo[g * 256 + 32] = x1p[2 * g + 1];
                const float u0 = bf_lo(x1p[2 * g]), u1 = bf_hi(x1p[2 * g]), u2 = bf_lo(x1p[2 * g + 1]), u3 = bf_hi(x1p[2 * g + 1]);
                s1a += u0 + u1; s2a += u0 * u0 + u1 * u1; s1b += u2 + u3; s2b += u2 * u2 + u3 * u3;
            }
            float ka = (q & 1) ? s2a : s1a, kb2 = (q & 1) ? s2b : s1b;
            ka += __shfl_xor_sync(~0u, (q & 1) ? s1a : s2a, 1); kb2 += __shfl_xor_sync(~0u, (q & 1) ? s1b : s2b, 1);
            const float kk = ((q & 2) ? kb2 : ka) + __shfl_xor_sync(~0u, (q & 2) ? ka : kb2, 2);
            ((float*)g_st)[(((2 * r + w) * 8 + j) * 64 + 16 * wi + lr + 4 * (q & 2)) * 2 + (q & 1)] = kk;
            __syncwarp();
            if (lane < 2) mbar_arrive(BAR(B_PUB + 4 + w));
        } else reg_def<14>(x1p);
        PROFC(15);
        uint32_t h2a[32], h2b[24];
        if (RUN(6)) {
            const int fa = 224 * fs + ((fs & 1) ? 96 : 0), fb = 224 * fs + ((fs & 1) ? 0 : 128);
            uint32_t* h2g = g_h2 + (size_t)r * (224 * 512) + (8 * w + 2 * wi) * 32 + lane;
            const uint64_t a0 = mkdesc(sb + OFF_Y + w * HALF, DT);
            const int s0 = sc ? 12 : 0;
            {
                WAIT(B_GFULL + 2 + w, 0);
                PROFC(16);
                float2 sa = make_float2(0.f, 0.f), sbb = sa;
#pragma unroll
                for (int jj = 0; jj < 8; jj++) {
                    const float2 u = lds2f(sb + OFF_X + X_STAT + w * 4096 + (jj * 64 + 16 * wi + lr) * 8), v = lds2f(sb + OFF_X + X_STAT + w * 4096 + (jj * 64 + 16 * wi + lr + 8) * 8);
                    sa.x += u.x; sa.y += u.y; sbb.x += v.x; sbb.y += v.y;
                }
                warp_arrive(BAR(B_EMPTY + 6));
                uint32_t ra2, na2, rb2, nb2;
                ln_coeffs(sa.x * (1.f / DM), sa.y * (1.f / DM), ra2, na2);
                ln_coeffs(sbb.x * (1.f / DM), sbb.y * (1.f / DM), rb2, nb2);
                const uint32_t ha = sb + OFF_Y + w * HALF + (lane >> 4) * 1024 + (2 * wi + ((lane >> 3) & 1)) * 128 + (lane & 7) * 16;
                const uint32_t sta = sb + M_ST + q * 16;
                auto prep = [&](int s, uint32_t* f) {
#pragma unroll
                    for (int i = 0; i < 2; i++) {
                        uint32_t x[4];
                        ldsm4(ha + (2 * s + i) * 2048, x);
                        const uint4 st = lds4(sta + (2 * s + i) * 64);
                        f[4 * i] = hfma2(hfma2(x[0], ra2, na2), st.x, st.y); f[4 * i + 1] = hfma2(hfma2(x[1], rb2, nb2), st.x, st.y);
                        f[4 * i + 2] = hfma2(hfma2(x[2], ra2, na2), st.z, st.w); f[4 * i + 3] = hfma2(hfma2(x[3], rb2, nb2), st.z, st.w);
                        stsm4(ha + (2 * s + i) * 2048, f[4 * i], f[4 * i + 1], f[4 * i + 2], f[4 * i + 3]);
                    }
                };
                float ac[128];
                uint32_t fr[2][8];
                reg_def<128>(ac);
                prep(s0, fr[0]);
                PROFC(17);
                int sl = 0, prev = 0;
#pragma unroll 1
                for (int s2 = s0; s2 < 14; s2 += 2) {
#pragma unroll
                    for (int e = 0; e < 2; e++) {
                        const int s = s2 + e;
                        const uint32_t* f = fr[e];
                        WAIT(B_FULL + sl, s >= 7);
                        const uint64_t bd = mkdesc(sb + slot_off(sl), DB128);
                        WG_FENCE();
                        wgmma_rs_256<1>(ac, f[0], f[1], f[2], f[3], bd, s != 0);
                        wgmma_rs_256<1>(ac, f[4], f[5], f[6], f[7], bd + 128, 1);
                        WG_COMMIT();
                        WG_WAIT(1);
                        if (s > 0) warp_arrive(BAR(B_EMPTY + prev));
                        if (s < 13) prep(s + 1, fr[e ^ 1]);
                        prev = sl; sl = sl == 6 ? 0 : sl + 1;
                    }
                }
                fence_async_smem();
                WG_WAIT(0);
                reg_fence<128>(ac);
                warp_arrive(BAR(B_EMPTY + 6));
                PROFC(18);
#pragma unroll
                for (int g = 0; g < 16; g++) {
                    h2a[2 * g] = hmul2(pack2_relu(ac[4 * g], ac[4 * g + 1]), pack2(ac[64 + 4 * g], ac[64 + 4 * g + 1]));
                    h2a[2 * g + 1] = hmul2(pack2_relu(ac[4 * g + 2], ac[4 * g + 3]), pack2(ac[64 + 4 * g + 2], ac[64 + 4 * g + 3]));
                    h2g[(fa / 8 + g) * 512] = h2a[2 * g]; h2g[(fa / 8 + g) * 512 + 32] = h2a[2 * g + 1];
                }
                warp_arrive(BAR(B_PUB + 6));
                bar_sync(1 + w, 128);
            }
            PROFC(19);
            {
                float ac[96];
                reg_def<96>(ac);
                int sl = 0, prev = 0;
#pragma unroll 1
                for (int s = s0; s < 14; s++) {
                    WAIT(B_FULL + sl, s >= 7);
                    const uint64_t ad = a0 + s * 256, bd = mkdesc(sb + slot_off(sl), dconst(2048, 512, 2));
                    WG_FENCE();
                    wgmma_ss_192<1>(ac, ad, bd, s != 0);
                    wgmma_ss_192<1>(ac, ad + 128, bd + 64, 1);
                    WG_COMMIT();
                    if (s > 0) { WG_WAIT(1); warp_arrive(BAR(B_EMPTY + prev)); }
                    prev = sl; sl = sl == 6 ? 0 : sl + 1;
                }
                WG_WAIT(0);
                reg_fence<96>(ac);
                __syncwarp();
                if (lane < 6) mbar_arrive(BAR(B_EMPTY + 6 + lane));
                asm volatile("barrier.cluster.wait.aligned;" ::: "memory");
                if (lane == 0 && !sc) {
                    uint32_t rb;
                    asm volatile("mapa.shared::cluster.u32 %0, %1, %2;" : "=r"(rb) : "r"(BAR(B_PEER)), "r"(kh ^ 1));
                    asm volatile("mbarrier.arrive.relaxed.cluster.shared::cluster.b64 _, [%0];" ::"r"(rb) : "memory");
                }
                PROFC(20);
#pragma unroll
                for (int g = 0; g < 12; g++) {
                    h2b[2 * g] = hmul2(pack2_relu(ac[4 * g], ac[4 * g + 1]), pack2(ac[48 + 4 * g], ac[48 + 4 * g + 1]));
                    h2b[2 * g + 1] = hmul2(pack2_relu(ac[4 * g + 2], ac[4 * g + 3]), pack2(ac[48 + 4 * g + 2], ac[48 + 4 * g + 3]));
                    h2g[(fb / 8 + g) * 512] = h2b[2 * g]; h2g[(fb / 8 + g) * 512 + 32] = h2b[2 * g + 1];
                }
                warp_arrive(BAR(B_PUB + 7));
            }
        } else { reg_def<32>(h2a); reg_def<24>(h2b); }
        PROFC(21);
        if (RUN(7)) {
            float ac[56];
            reg_def<56>(ac);
            constexpr uint64_t DAN = dconst(2048, 128, 0);
#pragma unroll
            for (int e = 0; e < 4; e++) {
                WAIT(B_FULL + e, 0);
                const uint64_t bd = mkdesc(sb + slot_off(e), DB128);
                const uint32_t* hh = e < 2 ? h2a + 16 * e : h2b + 16 * (e - 2);
                WG_FENCE();
#pragma unroll
                for (int k = 0; k < (e < 3 ? 4 : 2); k++) wgmma_rs_112<1>(ac, hh[4 * k], hh[4 * k + 1], hh[4 * k + 2], hh[4 * k + 3], bd + (k >> 1) * 512 + (k & 1) * 128, (e | k) != 0);
                WG_COMMIT();
                if (e > 0) { WG_WAIT(1); warp_arrive(BAR(B_EMPTY + e - 1)); }
            }
            PROFC(22);
            int sl = 4, prev = 3;
#pragma unroll 1
            for (int e = 4; e < 25; e++) {
                WAIT(B_FULL + sl, e >= 12 && e < 24);
                if (e == 16) PROFC(23);
                const uint32_t sa = sb + slot_off(sl);
                const uint64_t ad = mkdesc(sa + 8192 + w * 1024, DAN), bd = mkdesc(sa, DB128);
                WG_FENCE();
                wgmma_ss_112<1>(ac, ad, bd, 1);
                wgmma_ss_112<1>(ac, ad + 256, bd + 128, 1);
                WG_COMMIT();
                if (e < 14) { WG_WAIT(1); warp_arrive(BAR(B_EMPTY + prev)); }
                prev = sl; sl = sl == 11 ? 0 : sl + 1;
            }
            mbar_wait_cluster(BAR(B_PEER), sc);
            WG_WAIT(0);
            reg_fence<56>(ac);
            PROFC(24);
            uint32_t rdst, rbar;
            asm volatile("mapa.shared::cluster.u32 %0, %1, %2;" : "=r"(rdst) : "r"(sb + OFF_Y + (5 + w) * 16384 + t * 16), "r"(kh ^ 1 ^ sc));
            asm volatile("mapa.shared::cluster.u32 %0, %1, %2;" : "=r"(rbar) : "r"(BAR(B_XCH + w)), "r"(kh ^ 1 ^ sc));
#define ACG(g, i) ac[4 * (((g) + 8) % 14) + (i)]
#pragma unroll
            for (int g = 0; g < 7; g++) {
                const float v0 = kh ? ACG(g, 0) : ACG(g + 7, 0), v1 = kh ? ACG(g, 1) : ACG(g + 7, 1);
                const float v2 = kh ? ACG(g, 2) : ACG(g + 7, 2), v3 = kh ? ACG(g, 3) : ACG(g + 7, 3);
                if (!sc) asm volatile("st.async.shared::cluster.mbarrier::complete_tx::bytes.v4.f32 [%0], {%1,%2,%3,%4}, [%5];"
                             ::"r"(rdst + g * 2048), "f"(v0), "f"(v1), "f"(v2), "f"(v3), "r"(rbar) : "memory");
            }
            mbar_wait_cluster(BAR(B_XCH + w), sc);
            PROFC(25);
            bf16* og = (sc ? (bf16*)(g_h2 + 16 * 224 * 512) : p.out + (size_t)128 * r * DM) + (size_t)ra * DM + 56 * j + 2 * q;
#pragma unroll
            for (int g = 0; g < 7; g++) {
                const uint4 rv = *(const uint4*)(smem + OFF_Y + (5 + w) * 16384 + t * 16 + g * 2048);
                const float2 gb = *(const float2*)(smem + M_G + 224 + (8 * g + 2 * q) * 4);
                const float v0 = (kh ? ACG(g + 7, 0) : ACG(g, 0)) + __uint_as_float(rv.x), v1 = (kh ? ACG(g + 7, 1) : ACG(g, 1)) + __uint_as_float(rv.y);
                const float v2 = (kh ? ACG(g + 7, 2) : ACG(g, 2)) + __uint_as_float(rv.z), v3 = (kh ? ACG(g + 7, 3) : ACG(g, 3)) + __uint_as_float(rv.w);
                *(uint32_t*)(og + 8 * g) = pack2(fmaf(gb.x, v0, bf_lo(x1p[2 * g])), fmaf(gb.y, v1, bf_hi(x1p[2 * g])));
                *(uint32_t*)(og + 8 * DM + 8 * g) = pack2(fmaf(gb.x, v2, bf_lo(x1p[2 * g + 1])), fmaf(gb.y, v3, bf_hi(x1p[2 * g + 1])));
            }
        }
        PROFC(26);
        warp_arrive(BAR(B_DONE));
    } else {
        const int lane = fresh_tid() & 31;
        const bool early = kh == 0, gemv = r < 14;
        const int mcol = early ? 16 * (4 * r + nq) : 2 * DM + 32 * (4 * r + nq);
        const uint32_t wmbuf = sb + OFF_Y + HALF;
        const int fa = 224 * fs + ((fs & 1) ? 96 : 0), fb = 224 * fs + ((fs & 1) ? 0 : 128);
        asm volatile("setmaxnreg.dec.sync.aligned.u32 56;");
        if (warp == 9) {
#pragma unroll
            for (int i = 56; i < 63; i++) init_e(BAR(i), 1);
            fence_async_smem();
        }
        if (warp == 8) { init_e(BAR(B_WMFULL), 2); fence_async_smem(); }
        bar_arrive(0, 384);
        asm volatile("barrier.cluster.arrive.relaxed.aligned;" ::: "memory");
        uint32_t target = 0;
        if (warp == 8) {
            if (!sc) {
                expect_e(BAR(B_WMFULL), gemv ? 28672 >> early : 0);
                if (early && gemv) { tma3_e(wmbuf, &p.wm, mcol, 0, 0, BAR(B_WMFULL)); tma3_e(wmbuf + 7168, &p.wm, mcol, 224, 0, BAR(B_WMFULL)); }
#pragma unroll 1
                for (int kb = 0; kb < 7; kb++) {
                    expect_e(BAR(B_XFULL + kb), 16384);
                    tma3_e(sb + OFF_X + kb * 16384, &p.xm, 64 * kb, 128 * r, 0, BAR(B_XFULL + kb));
                }
            }
#pragma unroll 1
            for (int mt = 0; mt < 4; mt++) {
                if (mt == 1) {
                    if (!early && gemv) {
#pragma unroll 1
                        for (int k = 0; k < 4; k++) tma3_e(wmbuf + k * 7168, &p.wm, mcol + (k >> 1) * 16, (k & 1) * 224, 0, BAR(B_WMFULL));
                    }
                    bar_sync(9, 384);
                    if (sc) return;
                    mbar_wait(BAR(B_MOD1), 0);
                    mbar_wait(BAR(B_WMFREE), 0);
                }
                if (mt == 2) mbar_wait(BAR(B_XFREE), 0);
                if (mt == 3) mbar_wait(BAR(B_VRFULL), 0);
                const uint32_t bar = BAR(mt == 3 ? B_WOFULL : B_FULLK + mt), dst = sb + (mt < 2 ? OFF_Y : OFF_X) + (mt & 1) * HALF;
                const int c0 = (mt < 2 ? DM + DM * mt : 0) + 56 * j - 8 * kh;
                if (!sc) {
                    expect_e(bar, HALF);
                    tma3_e(dst, mt == 3 ? &p.wo : &p.qkv, c0, 0, 0, bar);
                    tma3_e(dst + HALF / 2, mt == 3 ? &p.wo : &p.qkv, c0, 224, 0, bar);
                }
            }
            expect_e(BAR(B_XCH), 14336);
            expect_e(BAR(B_XCH + 1), 14336);
        } else {
            if (warp == 10 && lane == 0 && !sc) {
                const uint32_t ticket = atomicAdd(&g_ticket, 1u);
                l2_prefetch((const char*)p.wqkv + (size_t)b * 9408, 9408);
                sts1(sb + M_EPOCH, ticket / NCTA);
            }
            if (warp == 11) {
#pragma unroll
                for (int i = 0; i < 8; i++) {
                    const int wd = lane + 32 * i;
                    const uint32_t cb = i < 7 ? __ldg((const uint32_t*)p.c + wd) : 0u;
                    sts1(wmbuf + 28672 + (wd >> 3) * 32 + (wd & 3) * 8 + (wd & 4), pack2(silu_bf(cb & 0xFFFFu), silu_bf(cb >> 16)));
                }
            }
            bar_sync(9, 384);
            if (sc) return;
            target = lds1(sb + M_EPOCH) + 1;
            const uint32_t tag = target & 0xFFFFu;
            if (warp == 11) {
                warp_arrive(BAR(B_WMFULL));
                mbar_wait(BAR(B_GEMV), 0);
                float sum = 0.f;
#pragma unroll
                for (int i = 0; i < 8; i++) sum += *(const float*)(smem + OFF_Y + HALF + 29696 + (i * 32 + (early ? lane & 15 : lane)) * 4);
                const uint32_t word = (pack2(sum, 0.f) << 16) | tag;
                if (gemv) {
                    uint32_t* mg = g_mod + mcol + (early ? (lane & 15) + (lane >> 4) * 4 * 6 * DM : lane);
#pragma unroll
                    for (int i = 0; i < 8; i++) if (i < 4 || !early) st_relaxed(mg + i * 6 * DM, word);
                }
                warp_arrive(BAR(B_WMFREE));
            }
            const uint4* modp = (const uint4*)g_mod + (r & 7) * (6 * DM / 4);
            const bool p2 = warp == 11;
            mbar_wait(BAR(p2 ? B_PUB : B_XFULL + 4), 0);
#pragma unroll 1
            for (int it = p2 ? 0 : warp - 9; it < (p2 ? 2 : warp - 8); it++) {
                const int i0 = lane + 32 * it, imax = p2 ? 251 : 223;
                uint4 v[4];
#pragma unroll 1
                for (int n = 0;; n++) {
                    uint32_t bad = 0;
#pragma unroll
                    for (int k = 0; k < 4; k++) {
                        const int i = min(i0 + 64 * k, imax);
                        v[k] = ld_relaxed4(modp + (i < 224 ? (p2 ? 336 : 0) + i : (i < 238 ? 14 * j + i : 14 * j + i + 322)));
                        bad |= (v[k].x ^ tag) | (v[k].y ^ tag) | (v[k].z ^ tag) | (v[k].w ^ tag);
                    }
                    if (!(bad & 0xFFFFu)) break;
                    if (n > SPIN_LIMIT) __trap();
                }
#pragma unroll
                for (int k = 0; k < 4; k++) {
                    const int i = min(i0 + 64 * k, imax);
                    if (i < 224) {
                        const int isc = i >= 112, c4 = i - 112 * isc;
                        const float one = isc ? 1.f : 0.f;
                        const uint32_t a = sb + M_ST + (c4 >> 2) * 64 + (c4 & 1) * 32 + (c4 & 2) * 4 + (isc ? 0 : 4);
                        sts1(a, pack2(bf_hi(v[k].x) + one, bf_hi(v[k].y) + one));
                        sts1(a + 16, pack2(bf_hi(v[k].z) + one, bf_hi(v[k].w) + one));
                    } else {
                        sts4(sb + M_G + (i - 224) * 16, make_uint4(v[k].x & 0xFFFF0000u, v[k].y & 0xFFFF0000u, v[k].z & 0xFFFF0000u, v[k].w & 0xFFFF0000u));
                    }
                }
                warp_arrive(BAR(p2 ? B_MOD2 : B_MOD1));
            }
            if (warp == 9) {
#pragma unroll 1
                for (int kv = 0; kv < 2; kv++) {
                    mbar_wait(BAR(B_PUB + kv), 0);
                    if (lane >= 1 && lane <= 2 && r >= lane) wait_flag(g_flag + kv * 128 + b - 8 * lane, target);
                    __syncwarp();
                    fence_async_global();
                    const uint32_t dst = sb + OFF_Y + (kv ? Y_VR : Y_K);
                    expect_e(BAR(B_KRFULL + kv), r >= 2 ? 28672 : r == 1 ? 14336 : 0);
                    if (r >= 2) bulk_e(dst, g_kv + (size_t)((b - 16) * 2 + kv) * 3584, 14336, BAR(B_KRFULL + kv));
                    if (r >= 1) bulk_e(dst + 14336, g_kv + (size_t)((b - 8) * 2 + kv) * 3584, 14336, BAR(B_KRFULL + kv));
                }
            } else if (warp == 11) {
                mbar_wait(BAR(B_VRFULL), 0);
                if (lane == 0) {
                    l2_prefetch((const char*)p.wg + (size_t)b * 12544, 12544);
                    l2_prefetch((const char*)p.wu + (size_t)b * 12544, 12544);
                    l2_prefetch((const char*)p.wd + (size_t)b * 12544, 12544);
                }
                __syncwarp();
            }
        }
        if (warp == 8 || warp == 11) {
            const int sec = warp == 11;
            int sl = 0;
#pragma unroll 1
            for (int s = 0; s < 28; s++) {
                if (s >= 1 && s < 6) mbar_wait(BAR(B_FULL + s - 1), 0);
                const bool pa = s < 14;
                const uint32_t half = pa ? 8192 : 6144;
                mbar_wait(BAR(B_EMPTY + sl), (s >= 7 && s < 14) || s >= 21);
                expect_e(BAR(B_FULL + sl), half);
                tma3_e(sb + slot_off(sl) + sec * half, &p.ga + (pa ? 0 : 2) + sec, 0, 32 * (pa ? s : s - 14), pa ? fa >> 6 : fb >> 5, BAR(B_FULL + sl));
                sl = sl == 6 ? 0 : sl + 1;
            }
            if (!sec) PROFH(3);
#pragma unroll 1
            for (int e = 0; e < 4; e++) {
                const uint32_t dst = sb + slot_off(e) + sec * 8192, bar = BAR(B_FULL + e);
                const int f = (e < 2 ? fa : fb) + 64 * (e & 1) + 32 * sec;
                mbar_wait(BAR(B_EMPTY + e), 0);
                expect_e(bar, e == 3 && sec ? 0 : 8192);
                if (!(e == 3 && sec)) { tma3_e(dst, &p.dn, 112 * nq + 48, f, 0, bar); tma3_e(dst + 4096, &p.dn, 112 * nq, f, 0, bar); }
            }
            sl = 4;
            int e = 4;
#pragma unroll 1
            for (int grp = 0; grp < 6; grp++) {
                const bool pa = grp < 3;
                int sidx = pa ? grp : grp - 3;
                sidx += sidx >= nq;
                const int ofs = 4 * kh + sidx;
                int f = 224 * ofs + ((ofs & 1) ? (pa ? 96 : 0) : (pa ? 0 : 128));
                if (sec && (grp == 0 || grp == 3)) { mbar_wait(BAR(B_HRDY + !pa), 0); fence_async_global(); }
#pragma unroll 1
                for (int k = pa ? 0 : 1; k < 4; k++, e++, f += 32) {
                    const uint32_t dst = sb + slot_off(sl), bar = BAR(B_FULL + sl);
                    mbar_wait(BAR(B_EMPTY + sl), e >= 12 && e < 24);
                    expect_e(bar, 8192);
                    if (!sec) { tma3_e(dst, &p.dn, 112 * nq + 48, f, 0, bar); tma3_e(dst + 4096, &p.dn, 112 * nq, f, 0, bar); }
                    else bulk_e(dst + 8192, g_h2 + (size_t)r * (224 * 512) + f * 64, 8192, bar);
                    sl = sl == 11 ? 0 : sl + 1;
                }
            }
            if (!sec) PROFH(4);
            mbar_wait(BAR(B_DONE), 0);
        } else if (warp == 9) {
#pragma unroll
            for (int ev = 0; ev < 4; ev++) expect_e(BAR(B_GFULL + ev), ev < 2 ? HALF : HALF + 4096);
            mbar_wait(BAR(B_PUB + 2), 0);
            const uint32_t* fp = g_flag + (2 + (lane >> 3)) * 128 + 8 * r + (lane & 7);
            const uint32_t* src = g_ox + (size_t)2 * r * 14336;
            const float2* ssrc = g_st + 2 * r * 512;
#pragma unroll 1
            for (int n = 0, ev = 0; ev < 4; n++) {
                if (ev == 1) mbar_wait(BAR(B_PUB + 3), 0);
                uint32_t ok = __ballot_sync(~0u, (int)(ld_relaxed(fp) - target) >= 0) >> (8 * ev);
                while ((ok & 0xFFu) == 0xFFu) {
                    asm volatile("fence.acquire.gpu;" ::: "memory");
                    fence_async_global();
                    const uint32_t bar = BAR(B_GFULL + ev);
                    bulk_e(sb + (ev == 0 ? OFF_X : OFF_Y + (ev & 1) * HALF), src + (ev >> 1) * (34 * 14336) + (ev & 1) * 14336, HALF, bar);
                    if (ev >= 2) bulk_e(sb + OFF_X + X_STAT + (ev & 1) * 4096, ssrc + (ev & 1) * 512, 4096, bar);
                    if (ev) PROFH(4 + ev);
                    ev++; ok >>= 8;
                }
                if (n > SPIN_LIMIT) __trap();
            }
#pragma unroll 1
            for (int ps = 0; ps < 2; ps++) {
                mbar_wait(BAR(B_PUB + 6 + ps), 0);
                if (lane < 4) wait_flag(g_flag + (6 + ps) * 128 + 8 * r + 2 * lane + kh, target);
                warp_arrive(BAR(B_HRDY + ps));
                PROFH(10 + ps);
            }
        } else {
            if (lane == 0) {
#pragma unroll 1
                for (int k = 0; k < 8; k++) {
                    mbar_wait(BAR(B_PUB + k), 0);
                    fence_gpu();
                    st_relaxed(g_flag + k * 128 + b, target);
                    if (k >= 3 && k <= 5) PROFH1(k - 3);
                }
            }
        }
    }
}

typedef CUresult (*EncodeFn)(CUtensorMap*, CUtensorMapDataType, cuuint32_t, void*, const cuuint64_t*, const cuuint64_t*, const cuuint32_t*,
                             const cuuint32_t*, CUtensorMapInterleave, CUtensorMapSwizzle, CUtensorMapL2promotion, CUtensorMapFloatOOBfill);

static void make_map(EncodeFn fn, CUtensorMap* m, const void* ptr, uint64_t d0, uint64_t d1, uint64_t d2, uint64_t s1, uint64_t s2,
                     uint32_t b0, uint32_t b1, uint32_t b2, CUtensorMapSwizzle sw) {
    cuuint64_t dims[3] = {d0, d1, d2}, strides[2] = {s1, s2};
    cuuint32_t box[3] = {b0, b1, b2}, es[3] = {1, 1, 1};
    CUresult rc = fn(m, CU_TENSOR_MAP_DATA_TYPE_BFLOAT16, 3, (void*)ptr, dims, strides, box, es, CU_TENSOR_MAP_INTERLEAVE_NONE, sw,
                     CU_TENSOR_MAP_L2_PROMOTION_L2_128B, CU_TENSOR_MAP_FLOAT_OOB_FILL_NONE);
    (void)rc;
}

extern "C" void kernel_launch(void* const* d_in, const int* in_sizes, int n_in, void* d_out, int out_size) {
    (void)in_sizes; (void)n_in; (void)out_size;
    static EncodeFn fn = nullptr;
    if (!fn) {
        cudaDriverEntryPointQueryResult st;
        cudaGetDriverEntryPoint("cuTensorMapEncodeTiled", (void**)&fn, cudaEnableDefault, &st);
        cudaFuncSetAttribute(fused_block_kernel, cudaFuncAttributeMaxDynamicSharedMemorySize, SMEM_BYTES);
    }
    Params p;
    p.x = (const bf16*)d_in[0];
    const bf16* wqkv = (const bf16*)d_in[1];
    p.wqkv = wqkv;
    p.wop = (const bf16*)d_in[2];
    p.wg = (const bf16*)d_in[4];
    p.wu = (const bf16*)d_in[5];
    p.wd = (const bf16*)d_in[6];
    p.c = (const bf16*)d_in[7];
    p.wmod = (const bf16*)d_in[8];
    p.out = (bf16*)d_out;
    p.zero = 0;
    make_map(fn, &p.wm, p.wmod, 2688, 448, 1, 5376, 5376 * 448, 16, 224, 1, CU_TENSOR_MAP_SWIZZLE_NONE);
    make_map(fn, &p.xm, p.x, 448, 2048, 1, 896, 896 * 2048, 64, 128, 1, CU_TENSOR_MAP_SWIZZLE_128B);
    make_map(fn, &p.qkv, wqkv, 1344, 448, 1, 2688, 2688 * 448, 64, 224, 1, CU_TENSOR_MAP_SWIZZLE_128B);
    make_map(fn, &p.wo, p.wop, 448, 448, 1, 896, 896 * 448, 64, 224, 1, CU_TENSOR_MAP_SWIZZLE_128B);
    make_map(fn, &p.ga, p.wg, 64, 448, 28, 3584, 128, 64, 32, 2, CU_TENSOR_MAP_SWIZZLE_128B);
    make_map(fn, &p.ua, p.wu, 64, 448, 28, 3584, 128, 64, 32, 2, CU_TENSOR_MAP_SWIZZLE_128B);
    make_map(fn, &p.gb, p.wg, 32, 448, 56, 3584, 64, 32, 32, 3, CU_TENSOR_MAP_SWIZZLE_64B);
    make_map(fn, &p.ub, p.wu, 32, 448, 56, 3584, 64, 32, 32, 3, CU_TENSOR_MAP_SWIZZLE_64B);
    make_map(fn, &p.dn, p.wd, 448, 1792, 1, 896, 896 * 1792, 64, 32, 1, CU_TENSOR_MAP_SWIZZLE_128B);
    fused_block_kernel<<<GRID, 384, SMEM_BYTES>>>(p);
}
```

```cpp
#include <cuda_runtime.h>
#include <cuda_bf16.h>
#include <cuda.h>
#include <stdint.h>

typedef __nv_bfloat16 bf16;

template<int TB> __device__ __forceinline__ void wgmma_rs_56(float* d, uint32_t a0, uint32_t a1, uint32_t a2, uint32_t a3, uint64_t db, int sd) {
  asm volatile("{\n.reg .pred p;\nsetp.ne.b32 p, %33, 0;\n"
    "wgmma.mma_async.sync.aligned.m64n56k16.f32.bf16.bf16 {%0,%1,%2,%3,%4,%5,%6,%7,%8,%9,%10,%11,%12,%13,%14,%15,%16,%17,%18,%19,%20,%21,%22,%23,%24,%25,%26,%27}, {%28,%29,%30,%31}, %32, p, 1, 1, %34;\n}\n"
    : "+f"(d[0]),"+f"(d[1]),"+f"(d[2]),"+f"(d[3]),"+f"(d[4]),"+f"(d[5]),"+f"(d[6]),"+f"(d[7]),"+f"(d[8]),"+f"(d[9]),"+f"(d[10]),"+f"(d[11]),"+f"(d[12]),"+f"(d[13]),"+f"(d[14]),"+f"(d[15]),"+f"(d[16]),"+f"(d[17]),"+f"(d[18]),"+f"(d[19]),"+f"(d[20]),"+f"(d[21]),"+f"(d[22]),"+f"(d[23]),"+f"(d[24]),"+f"(d[25]),"+f"(d[26]),"+f"(d[27])
    : "r"(a0), "r"(a1), "r"(a2), "r"(a3), "l"(db), "r"(sd), "n"(TB));
}
template<int TB> __device__ __forceinline__ void wgmma_ss_56(float* d, uint64_t da, uint64_t db, int sd) {
  asm volatile("{\n.reg .pred p;\nsetp.ne.b32 p, %30, 0;\n"
    "wgmma.mma_async.sync.aligned.m64n56k16.f32.bf16.bf16 {%0,%1,%2,%3,%4,%5,%6,%7,%8,%9,%10,%11,%12,%13,%14,%15,%16,%17,%18,%19,%20,%21,%22,%23,%24,%25,%26,%27}, %28, %29, p, 1, 1, 0, %31;\n}\n"
    : "+f"(d[0]),"+f"(d[1]),"+f"(d[2]),"+f"(d[3]),"+f"(d[4]),"+f"(d[5]),"+f"(d[6]),"+f"(d[7]),"+f"(d[8]),"+f"(d[9]),"+f"(d[10]),"+f"(d[11]),"+f"(d[12]),"+f"(d[13]),"+f"(d[14]),"+f"(d[15]),"+f"(d[16]),"+f"(d[17]),"+f"(d[18]),"+f"(d[19]),"+f"(d[20]),"+f"(d[21]),"+f"(d[22]),"+f"(d[23]),"+f"(d[24]),"+f"(d[25]),"+f"(d[26]),"+f"(d[27])
    : "l"(da), "l"(db), "r"(sd), "n"(TB));
}
template<int TB> __device__ __forceinline__ void wgmma_rs_256(float* d, uint32_t a0, uint32_t a1, uint32_t a2, uint32_t a3, uint64_t db, int sd) {
  asm volatile("{\n.reg .pred p;\nsetp.ne.b32 p, %133, 0;\n"
    "wgmma.mma_async.sync.aligned.m64n256k16.f32.bf16.bf16 {%0,%1,%2,%3,%4,%5,%6,%7,%8,%9,%10,%11,%12,%13,%14,%15,%16,%17,%18,%19,%20,%21,%22,%23,%24,%25,%26,%27,%28,%29,%30,%31,%32,%33,%34,%35,%36,%37,%38,%39,%40,%41,%42,%43,%44,%45,%46,%47,%48,%49,%50,%51,%52,%53,%54,%55,%56,%57,%58,%59,%60,%61,%62,%63,%64,%65,%66,%67,%68,%69,%70,%71,%72,%73,%74,%75,%76,%77,%78,%79,%80,%81,%82,%83,%84,%85,%86,%87,%88,%89,%90,%91,%92,%93,%94,%95,%96,%97,%98,%99,%100,%101,%102,%103,%104,%105,%106,%107,%108,%109,%110,%111,%112,%113,%114,%115,%116,%117,%118,%119,%120,%121,%122,%123,%124,%125,%126,%127}, {%128,%129,%130,%131}, %132, p, 1, 1, %134;\n}\n"
    : "+f"(d[0]),"+f"(d[1]),"+f"(d[2]),"+f"(d[3]),"+f"(d[4]),"+f"(d[5]),"+f"(d[6]),"+f"(d[7]),"+f"(d[8]),"+f"(d[9]),"+f"(d[10]),"+f"(d[11]),"+f"(d[12]),"+f"(d[13]),"+f"(d[14]),"+f"(d[15]),"+f"(d[16]),"+f"(d[17]),"+f"(d[18]),"+f"(d[19]),"+f"(d[20]),"+f"(d[21]),"+f"(d[22]),"+f"(d[23]),"+f"(d[24]),"+f"(d[25]),"+f"(d[26]),"+f"(d[27]),"+f"(d[28]),"+f"(d[29]),"+f"(d[30]),"+f"(d[31]),"+f"(d[32]),"+f"(d[33]),"+f"(d[34]),"+f"(d[35]),"+f"(d[36]),"+f"(d[37]),"+f"(d[38]),"+f"(d[39]),"+f"(d[40]),"+f"(d[41]),"+f"(d[42]),"+f"(d[43]),"+f"(d[44]),"+f"(d[45]),"+f"(d[46]),"+f"(d[47]),"+f"(d[48]),"+f"(d[49]),"+f"(d[50]),"+f"(d[51]),"+f"(d[52]),"+f"(d[53]),"+f"(d[54]),"+f"(d[55]),"+f"(d[56]),"+f"(d[57]),"+f"(d[58]),"+f"(d[59]),"+f"(d[60]),"+f"(d[61]),"+f"(d[62]),"+f"(d[63]),"+f"(d[64]),"+f"(d[65]),"+f"(d[66]),"+f"(d[67]),"+f"(d[68]),"+f"(d[69]),"+f"(d[70]),"+f"(d[71]),"+f"(d[72]),"+f"(d[73]),"+f"(d[74]),"+f"(d[75]),"+f"(d[76]),"+f"(d[77]),"+f"(d[78]),"+f"(d[79]),"+f"(d[80]),"+f"(d[81]),"+f"(d[82]),"+f"(d[83]),"+f"(d[84]),"+f"(d[85]),"+f"(d[86]),"+f"(d[87]),"+f"(d[88]),"+f"(d[89]),"+f"(d[90]),"+f"(d[91]),"+f"(d[92]),"+f"(d[93]),"+f"(d[94]),"+f"(d[95]),"+f"(d[96]),"+f"(d[97]),"+f"(d[98]),"+f"(d[99]),"+f"(d[100]),"+f"(d[101]),"+f"(d[102]),"+f"(d[103]),"+f"(d[104]),"+f"(d[105]),"+f"(d[106]),"+f"(d[107]),"+f"(d[108]),"+f"(d[109]),"+f"(d[110]),"+f"(d[111]),"+f"(d[112]),"+f"(d[113]),"+f"(d[114]),"+f"(d[115]),"+f"(d[116]),"+f"(d[117]),"+f"(d[118]),"+f"(d[119]),"+f"(d[120]),"+f"(d[121]),"+f"(d[122]),"+f"(d[123]),"+f"(d[124]),"+f"(d[125]),"+f"(d[126]),"+f"(d[127])
    : "r"(a0), "r"(a1), "r"(a2), "r"(a3), "l"(db), "r"(sd), "n"(TB));
}
template<int TB> __device__ __forceinline__ void wgmma_ss_192(float* d, uint64_t da, uint64_t db, int sd) {
  asm volatile("{\n.reg .pred p;\nsetp.ne.b32 p, %98, 0;\n"
    "wgmma.mma_async.sync.aligned.m64n192k16.f32.bf16.bf16 {%0,%1,%2,%3,%4,%5,%6,%7,%8,%9,%10,%11,%12,%13,%14,%15,%16,%17,%18,%19,%20,%21,%22,%23,%24,%25,%26,%27,%28,%29,%30,%31,%32,%33,%34,%35,%36,%37,%38,%39,%40,%41,%42,%43,%44,%45,%46,%47,%48,%49,%50,%51,%52,%53,%54,%55,%56,%57,%58,%59,%60,%61,%62,%63,%64,%65,%66,%67,%68,%69,%70,%71,%72,%73,%74,%75,%76,%77,%78,%79,%80,%81,%82,%83,%84,%85,%86,%87,%88,%89,%90,%91,%92,%93,%94,%95}, %96, %97, p, 1, 1, 0, %99;\n}\n"
    : "+f"(d[0]),"+f"(d[1]),"+f"(d[2]),"+f"(d[3]),"+f"(d[4]),"+f"(d[5]),"+f"(d[6]),"+f"(d[7]),"+f"(d[8]),"+f"(d[9]),"+f"(d[10]),"+f"(d[11]),"+f"(d[12]),"+f"(d[13]),"+f"(d[14]),"+f"(d[15]),"+f"(d[16]),"+f"(d[17]),"+f"(d[18]),"+f"(d[19]),"+f"(d[20]),"+f"(d[21]),"+f"(d[22]),"+f"(d[23]),"+f"(d[24]),"+f"(d[25]),"+f"(d[26]),"+f"(d[27]),"+f"(d[28]),"+f"(d[29]),"+f"(d[30]),"+f"(d[31]),"+f"(d[32]),"+f"(d[33]),"+f"(d[34]),"+f"(d[35]),"+f"(d[36]),"+f"(d[37]),"+f"(d[38]),"+f"(d[39]),"+f"(d[40]),"+f"(d[41]),"+f"(d[42]),"+f"(d[43]),"+f"(d[44]),"+f"(d[45]),"+f"(d[46]),"+f"(d[47]),"+f"(d[48]),"+f"(d[49]),"+f"(d[50]),"+f"(d[51]),"+f"(d[52]),"+f"(d[53]),"+f"(d[54]),"+f"(d[55]),"+f"(d[56]),"+f"(d[57]),"+f"(d[58]),"+f"(d[59]),"+f"(d[60]),"+f"(d[61]),"+f"(d[62]),"+f"(d[63]),"+f"(d[64]),"+f"(d[65]),"+f"(d[66]),"+f"(d[67]),"+f"(d[68]),"+f"(d[69]),"+f"(d[70]),"+f"(d[71]),"+f"(d[72]),"+f"(d[73]),"+f"(d[74]),"+f"(d[75]),"+f"(d[76]),"+f"(d[77]),"+f"(d[78]),"+f"(d[79]),"+f"(d[80]),"+f"(d[81]),"+f"(d[82]),"+f"(d[83]),"+f"(d[84]),"+f"(d[85]),"+f"(d[86]),"+f"(d[87]),"+f"(d[88]),"+f"(d[89]),"+f"(d[90]),"+f"(d[91]),"+f"(d[92]),"+f"(d[93]),"+f"(d[94]),"+f"(d[95])
    : "l"(da), "l"(db), "r"(sd), "n"(TB));
}
template<int TB> __device__ __forceinline__ void wgmma_ss_112(float* d, uint64_t da, uint64_t db, int sd) {
  asm volatile("{\n.reg .pred p;\nsetp.ne.b32 p, %58, 0;\n"
    "wgmma.mma_async.sync.aligned.m64n112k16.f32.bf16.bf16 {%0,%1,%2,%3,%4,%5,%6,%7,%8,%9,%10,%11,%12,%13,%14,%15,%16,%17,%18,%19,%20,%21,%22,%23,%24,%25,%26,%27,%28,%29,%30,%31,%32,%33,%34,%35,%36,%37,%38,%39,%40,%41,%42,%43,%44,%45,%46,%47,%48,%49,%50,%51,%52,%53,%54,%55}, %56, %57, p, 1, 1, 0, %59;\n}\n"
    : "+f"(d[0]),"+f"(d[1]),"+f"(d[2]),"+f"(d[3]),"+f"(d[4]),"+f"(d[5]),"+f"(d[6]),"+f"(d[7]),"+f"(d[8]),"+f"(d[9]),"+f"(d[10]),"+f"(d[11]),"+f"(d[12]),"+f"(d[13]),"+f"(d[14]),"+f"(d[15]),"+f"(d[16]),"+f"(d[17]),"+f"(d[18]),"+f"(d[19]),"+f"(d[20]),"+f"(d[21]),"+f"(d[22]),"+f"(d[23]),"+f"(d[24]),"+f"(d[25]),"+f"(d[26]),"+f"(d[27]),"+f"(d[28]),"+f"(d[29]),"+f"(d[30]),"+f"(d[31]),"+f"(d[32]),"+f"(d[33]),"+f"(d[34]),"+f"(d[35]),"+f"(d[36]),"+f"(d[37]),"+f"(d[38]),"+f"(d[39]),"+f"(d[40]),"+f"(d[41]),"+f"(d[42]),"+f"(d[43]),"+f"(d[44]),"+f"(d[45]),"+f"(d[46]),"+f"(d[47]),"+f"(d[48]),"+f"(d[49]),"+f"(d[50]),"+f"(d[51]),"+f"(d[52]),"+f"(d[53]),"+f"(d[54]),"+f"(d[55])
    : "l"(da), "l"(db), "r"(sd), "n"(TB));
}
template<int TB> __device__ __forceinline__ void wgmma_rs_112(float* d, uint32_t a0, uint32_t a1, uint32_t a2, uint32_t a3, uint64_t db, int sd) {
  asm volatile("{\n.reg .pred p;\nsetp.ne.b32 p, %61, 0;\n"
    "wgmma.mma_async.sync.aligned.m64n112k16.f32.bf16.bf16 {%0,%1,%2,%3,%4,%5,%6,%7,%8,%9,%10,%11,%12,%13,%14,%15,%16,%17,%18,%19,%20,%21,%22,%23,%24,%25,%26,%27,%28,%29,%30,%31,%32,%33,%34,%35,%36,%37,%38,%39,%40,%41,%42,%43,%44,%45,%46,%47,%48,%49,%50,%51,%52,%53,%54,%55}, {%56,%57,%58,%59}, %60, p, 1, 1, %62;\n}\n"
    : "+f"(d[0]),"+f"(d[1]),"+f"(d[2]),"+f"(d[3]),"+f"(d[4]),"+f"(d[5]),"+f"(d[6]),"+f"(d[7]),"+f"(d[8]),"+f"(d[9]),"+f"(d[10]),"+f"(d[11]),"+f"(d[12]),"+f"(d[13]),"+f"(d[14]),"+f"(d[15]),"+f"(d[16]),"+f"(d[17]),"+f"(d[18]),"+f"(d[19]),"+f"(d[20]),"+f"(d[21]),"+f"(d[22]),"+f"(d[23]),"+f"(d[24]),"+f"(d[25]),"+f"(d[26]),"+f"(d[27]),"+f"(d[28]),"+f"(d[29]),"+f"(d[30]),"+f"(d[31]),"+f"(d[32]),"+f"(d[33]),"+f"(d[34]),"+f"(d[35]),"+f"(d[36]),"+f"(d[37]),"+f"(d[38]),"+f"(d[39]),"+f"(d[40]),"+f"(d[41]),"+f"(d[42]),"+f"(d[43]),"+f"(d[44]),"+f"(d[45]),"+f"(d[46]),"+f"(d[47]),"+f"(d[48]),"+f"(d[49]),"+f"(d[50]),"+f"(d[51]),"+f"(d[52]),"+f"(d[53]),"+f"(d[54]),"+f"(d[55])
    : "r"(a0), "r"(a1), "r"(a2), "r"(a3), "l"(db), "r"(sd), "n"(TB));
}

constexpr int DM = 448;
constexpr int NCTA = 128;
#define MAPPING 1
#define GRID 132
#define PINGPONG 0
#define NPOLL 4
#define POLL_GAP 150
#define ALLATONCE 0
#define MAP_S 4
constexpr int SPIN_LIMIT = 1 << 22;

constexpr uint32_t OFF_X = 0, OFF_Y = 114688, OFF_MISC = 229376, SMEM_BYTES = 232448;
constexpr uint32_t Y_VR = 0, Y_K = 28672, Y_KOWN = 57344, Y_VOWN = 71680, Y_Q = 86016;
constexpr uint32_t HALF = 57344;
constexpr uint32_t M_BAR = OFF_MISC;
constexpr uint32_t M_ST = OFF_MISC + 512;
constexpr uint32_t M_G = OFF_MISC + 2304;
constexpr uint32_t M_EPOCH = OFF_MISC + 3040;
enum { B_XFULL = 0, B_FULLK = 7, B_FULLV = 8, B_FULLQ, B_KRFULL, B_VRFULL, B_WOFULL, B_XCH, B_FULL = 16, B_MOD1 = 28, B_MOD2, B_WMFULL,
       B_EMPTY = 32, B_XFREE = B_EMPTY + 12, B_GEMV, B_PEER, B_DONE,
       B_PUB = 48,
       B_WMFREE = 56, B_HRDY, B_GFULL = B_HRDY + 2 };
constexpr uint32_t X_STAT = 49152;

__device__ uint32_t g_ticket;
__device__ __align__(128) uint32_t g_mod[8 * 6 * DM];
__device__ __align__(128) uint32_t g_flag[8 * 16 * 8];
__device__ __align__(128) uint32_t g_kv[17 * 8 * 2 * 3584];
__device__ __align__(128) uint32_t g_ox[2 * 34 * 14336];
#define g_o g_ox
#define g_x1 (g_ox + 34 * 14336)
__device__ __align__(128) float2 g_st[34 * 8 * 64];
__device__ __align__(128) uint32_t g_h2[17 * 224 * 512];
#define PROFH(id)
#define PROFH1(id)
#define PROFC(id)

struct alignas(64) Params {
    CUtensorMap wm, xm, qkv, wo, ga, ua, gb, ub, dn;
    const bf16 *x, *c, *wqkv, *wmod, *wg, *wu, *wd, *wop;
    bf16* out;
    uint32_t zero;
};

__device__ __forceinline__ void mbar_init(uint32_t bar, int cnt) { asm volatile("mbarrier.init.shared::cta.b64 [%0], %1;" ::"r"(bar), "r"(cnt) : "memory"); }
__device__ __forceinline__ void mbar_expect_tx(uint32_t bar, uint32_t bytes) { asm volatile("mbarrier.arrive.expect_tx.shared::cta.b64 _, [%0], %1;" ::"r"(bar), "r"(bytes) : "memory"); }
__device__ __forceinline__ void mbar_arrive(uint32_t bar) { asm volatile("mbarrier.arrive.shared::cta.b64 _, [%0];" ::"r"(bar) : "memory"); }
__device__ __forceinline__ void mbar_wait(uint32_t bar, uint32_t parity) {
    uint32_t ok; int n = 0;
    do {
        asm volatile("{\n.reg .pred p;\nmbarrier.try_wait.parity.shared::cta.b64 p, [%1], %2;\nselp.u32 %0, 1, 0, p;\n}" : "=r"(ok) : "r"(bar), "r"(parity) : "memory");
        if (++n > SPIN_LIMIT) __trap();
    } while (!ok);
}
__device__ __forceinline__ void mbar_wait_cluster(uint32_t bar, uint32_t parity) {
    uint32_t ok; int n = 0;
    do {
        asm volatile("{\n.reg .pred p;\nmbarrier.try_wait.parity.acquire.cluster.shared::cta.b64 p, [%1], %2;\nselp.u32 %0, 1, 0, p;\n}" : "=r"(ok) : "r"(bar), "r"(parity) : "memory");
        if (++n > SPIN_LIMIT) __trap();
    } while (!ok);
}
__device__ __forceinline__ void warp_arrive(uint32_t bar) {
    __syncwarp();
    asm volatile("{\n.reg .pred p;\nelect.sync _|p, 0xffffffff;\n@p mbarrier.arrive.shared::cta.b64 _, [%0];\n}" ::"r"(bar) : "memory");
}
__device__ __forceinline__ int opaque(int v) { return __shfl_sync(~0u, v, 0); }
__device__ __forceinline__ int fresh_tid() { int v; asm volatile("mov.u32 %0, %%tid.x;" : "=r"(v)); return v; }
__device__ __forceinline__ void bar_sync(int id, int n) { asm volatile("bar.sync %0, %1;" ::"r"(id), "r"(n) : "memory"); }
__device__ __forceinline__ void bar_arrive(int id, int n) { asm volatile("bar.arrive %0, %1;" ::"r"(id), "r"(n) : "memory"); }
__device__ __forceinline__ void fence_async_smem() { asm volatile("fence.proxy.async.shared::cta;" ::: "memory"); }
__device__ __forceinline__ void fence_async_global() { asm volatile("fence.proxy.async.global;" ::: "memory"); }
__device__ __forceinline__ void fence_gpu() { asm volatile("fence.release.gpu;" ::: "memory"); }
__device__ __forceinline__ void tma3(uint32_t dst, const CUtensorMap* m, int c0, int c1, int c2, uint32_t bar) {
    asm volatile("cp.async.bulk.tensor.3d.shared::cluster.global.mbarrier::complete_tx::bytes [%0], [%1, {%3, %4, %5}], [%2];"
                 ::"r"(dst), "l"(m), "r"(bar), "r"(c0), "r"(c1), "r"(c2) : "memory");
}
__device__ __forceinline__ void bulk_load(uint32_t dst, const void* src, uint32_t bytes, uint32_t bar) {
    asm volatile("cp.async.bulk.shared::cluster.global.mbarrier::complete_tx::bytes [%0], [%1], %2, [%3];" ::"r"(dst), "l"(src), "r"(bytes), "r"(bar) : "memory");
}
__device__ __forceinline__ void expect_e(uint32_t bar, uint32_t bytes) {
    asm volatile("{\n.reg .pred p;\nelect.sync _|p, 0xffffffff;\n@p mbarrier.arrive.expect_tx.shared::cta.b64 _, [%0], %1;\n}" ::"r"(bar), "r"(bytes) : "memory");
}
__device__ __forceinline__ void tma3_e(uint32_t dst, const CUtensorMap* m, int c0, int c1, int c2, uint32_t bar) {
    asm volatile("{\n.reg .pred p;\nelect.sync _|p, 0xffffffff;\n@p cp.async.bulk.tensor.3d.shared::cluster.global.mbarrier::complete_tx::bytes [%0], [%1, {%3, %4, %5}], [%2];\n}"
                 ::"r"(dst), "l"(m), "r"(bar), "r"(c0), "r"(c1), "r"(c2) : "memory");
}
__device__ __forceinline__ void bulk_e(uint32_t dst, const void* src, uint32_t bytes, uint32_t bar) {
    asm volatile("{\n.reg .pred p;\nelect.sync _|p, 0xffffffff;\n@p cp.async.bulk.shared::cluster.global.mbarrier::complete_tx::bytes [%0], [%1], %2, [%3];\n}"
                 ::"r"(dst), "l"(src), "r"(bytes), "r"(bar) : "memory");
}
__device__ __forceinline__ void init_e(uint32_t bar, int cnt) {
    asm volatile("{\n.reg .pred p;\nelect.sync _|p, 0xffffffff;\n@p mbarrier.init.shared::cta.b64 [%0], %1;\n}" ::"r"(bar), "r"(cnt) : "memory");
}
__device__ __forceinline__ void l2_prefetch_e(const void* src, uint32_t bytes) {
    asm volatile("{\n.reg .pred p;\nelect.sync _|p, 0xffffffff;\n@p cp.async.bulk.prefetch.L2.global [%0], %1;\n}" ::"l"(src), "r"(bytes) : "memory");
}
__device__ __forceinline__ uint32_t ld_relaxed(const uint32_t* p) { uint32_t v; asm volatile("ld.relaxed.gpu.global.u32 %0, [%1];" : "=r"(v) : "l"(p) : "memory"); return v; }
__device__ __forceinline__ void st_relaxed(uint32_t* p, uint32_t v) { asm volatile("st.relaxed.gpu.global.u32 [%0], %1;" ::"l"(p), "r"(v) : "memory"); }
__device__ __forceinline__ uint4 ld_relaxed4(const uint4* p) { uint4 v; asm volatile("ld.relaxed.gpu.global.v4.u32 {%0,%1,%2,%3}, [%4];" : "=r"(v.x), "=r"(v.y), "=r"(v.z), "=r"(v.w) : "l"(p) : "memory"); return v; }
__device__ __forceinline__ void st_relaxed4(uint4* p, uint4 v) { asm volatile("st.relaxed.gpu.global.v4.u32 [%0], {%1,%2,%3,%4};" ::"l"(p), "r"(v.x), "r"(v.y), "r"(v.z), "r"(v.w) : "memory"); }
__device__ __forceinline__ uint4 ldg_nc4(const void* p) { uint4 v; asm volatile("ld.global.nc.L1::no_allocate.v4.u32 {%0,%1,%2,%3}, [%4];" : "=r"(v.x), "=r"(v.y), "=r"(v.z), "=r"(v.w) : "l"(p)); return v; }
__device__ __forceinline__ uint32_t ldg_nc(const void* p) { uint32_t v; asm volatile("ld.global.nc.u32 %0, [%1];" : "=r"(v) : "l"(p)); return v; }
__device__ __forceinline__ uint32_t ld_acquire(const uint32_t* p) { uint32_t v; asm volatile("ld.acquire.gpu.global.u32 %0, [%1];" : "=r"(v) : "l"(p) : "memory"); return v; }
__device__ __forceinline__ uint4 lds4(uint32_t a) { uint4 v; asm volatile("ld.shared.v4.u32 {%0,%1,%2,%3}, [%4];" : "=r"(v.x), "=r"(v.y), "=r"(v.z), "=r"(v.w) : "r"(a) : "memory"); return v; }
__device__ __forceinline__ float2 lds2f(uint32_t a) { float2 v; asm volatile("ld.shared.v2.f32 {%0,%1}, [%2];" : "=f"(v.x), "=f"(v.y) : "r"(a) : "memory"); return v; }
__device__ __forceinline__ uint32_t lds1(uint32_t a) { uint32_t v; asm volatile("ld.shared.u32 %0, [%1];" : "=r"(v) : "r"(a) : "memory"); return v; }
__device__ __forceinline__ void sts4(uint32_t a, uint4 v) { asm volatile("st.shared.v4.u32 [%0], {%1,%2,%3,%4};" ::"r"(a), "r"(v.x), "r"(v.y), "r"(v.z), "r"(v.w) : "memory"); }
__device__ __forceinline__ void sts2(uint32_t a, uint32_t x, uint32_t y) { asm volatile("st.shared.v2.u32 [%0], {%1,%2};" ::"r"(a), "r"(x), "r"(y) : "memory"); }
__device__ __forceinline__ void sts1(uint32_t a, uint32_t v) { asm volatile("st.shared.u32 [%0], %1;" ::"r"(a), "r"(v) : "memory"); }
__device__ __forceinline__ void stsm4(uint32_t a, uint32_t r0, uint32_t r1, uint32_t r2, uint32_t r3) {
    asm volatile("stmatrix.sync.aligned.m8n8.x4.shared.b16 [%0], {%1,%2,%3,%4};" ::"r"(a), "r"(r0), "r"(r1), "r"(r2), "r"(r3));
}
__device__ __forceinline__ uint32_t pack2(float lo, float hi) { uint32_t r; asm("cvt.rn.bf16x2.f32 %0, %1, %2;" : "=r"(r) : "f"(hi), "f"(lo)); return r; }
__device__ __forceinline__ uint32_t pack2_relu(float lo, float hi) { uint32_t r; asm("cvt.rn.relu.bf16x2.f32 %0, %1, %2;" : "=r"(r) : "f"(hi), "f"(lo)); return r; }
__device__ __forceinline__ uint32_t hfma2(uint32_t a, uint32_t b, uint32_t c) { uint32_t r; asm("fma.rn.bf16x2 %0, %1, %2, %3;" : "=r"(r) : "r"(a), "r"(b), "r"(c)); return r; }
__device__ __forceinline__ uint32_t hmul2(uint32_t a, uint32_t b) { uint32_t r; asm("mul.rn.bf16x2 %0, %1, %2;" : "=r"(r) : "r"(a), "r"(b)); return r; }
__device__ __forceinline__ float bf_lo(uint32_t v) { return __uint_as_float(v << 16); }
__device__ __forceinline__ float bf_hi(uint32_t v) { return __uint_as_float(v & 0xFFFF0000u); }
__device__ __forceinline__ float bf_round(float v) { return bf_lo(pack2(v, 0.f)); }
__device__ __forceinline__ float ex2(float x) { float r; asm("ex2.approx.ftz.f32 %0, %1;" : "=f"(r) : "f"(x)); return r; }
__device__ __forceinline__ void mma16816(float* d, uint32_t a0, uint32_t a1, uint32_t a2, uint32_t a3, uint32_t b0, uint32_t b1) {
    asm("mma.sync.aligned.m16n8k16.row.col.f32.bf16.bf16.f32 {%0,%1,%2,%3}, {%4,%5,%6,%7}, {%8,%9}, {%0,%1,%2,%3};"
        : "+f"(d[0]), "+f"(d[1]), "+f"(d[2]), "+f"(d[3]) : "r"(a0), "r"(a1), "r"(a2), "r"(a3), "r"(b0), "r"(b1));
}
__device__ __forceinline__ void mma16816_first(float* d, uint32_t a0, uint32_t a1, uint32_t a2, uint32_t a3, uint32_t b0, uint32_t b1) {
    asm volatile("mma.sync.aligned.m16n8k16.row.col.f32.bf16.bf16.f32 {%0,%1,%2,%3}, {%4,%5,%6,%7}, {%8,%9}, {%10,%10,%10,%10};"
        : "=f"(d[0]), "=f"(d[1]), "=f"(d[2]), "=f"(d[3]) : "r"(a0), "r"(a1), "r"(a2), "r"(a3), "r"(b0), "r"(b1), "f"(0.f));
}
__device__ __forceinline__ void mma16816_v(float* d, uint32_t a0, uint32_t a1, uint32_t a2, uint32_t a3, uint32_t b0, uint32_t b1) {
    asm volatile("mma.sync.aligned.m16n8k16.row.col.f32.bf16.bf16.f32 {%0,%1,%2,%3}, {%4,%5,%6,%7}, {%8,%9}, {%0,%1,%2,%3};"
        : "+f"(d[0]), "+f"(d[1]), "+f"(d[2]), "+f"(d[3]) : "r"(a0), "r"(a1), "r"(a2), "r"(a3), "r"(b0), "r"(b1));
}
__device__ __forceinline__ void mma1688(float* d, uint32_t a0, uint32_t a1, uint32_t b0) {
    asm("mma.sync.aligned.m16n8k8.row.col.f32.bf16.bf16.f32 {%0,%1,%2,%3}, {%4,%5}, {%6}, {%0,%1,%2,%3};"
        : "+f"(d[0]), "+f"(d[1]), "+f"(d[2]), "+f"(d[3]) : "r"(a0), "r"(a1), "r"(b0));
}
__device__ __forceinline__ void ldsm4(uint32_t a, uint32_t* r) {
    asm volatile("ldmatrix.sync.aligned.m8n8.x4.shared.b16 {%0,%1,%2,%3}, [%4];" : "=r"(r[0]), "=r"(r[1]), "=r"(r[2]), "=r"(r[3]) : "r"(a));
}
__device__ __forceinline__ void ldsm4t(uint32_t a, uint32_t* r) {
    asm volatile("ldmatrix.sync.aligned.m8n8.x4.trans.shared.b16 {%0,%1,%2,%3}, [%4];" : "=r"(r[0]), "=r"(r[1]), "=r"(r[2]), "=r"(r[3]) : "r"(a));
}
__device__ __forceinline__ float rcp(float x) { float r; asm("rcp.approx.ftz.f32 %0, %1;" : "=f"(r) : "f"(x)); return r; }
__device__ __forceinline__ uint2 ld_relaxed2(const void* p) { uint2 v; asm volatile("ld.relaxed.gpu.global.v2.u32 {%0,%1}, [%2];" : "=r"(v.x), "=r"(v.y) : "l"(p) : "memory"); return v; }
__device__ __forceinline__ void st_relaxed2(void* p, uint32_t x, uint32_t y) { asm volatile("st.relaxed.gpu.global.v2.u32 [%0], {%1,%2};" ::"l"(p), "r"(max(x, 1u)), "r"(max(y, 1u)) : "memory"); }
__device__ __forceinline__ constexpr uint64_t dconst(uint32_t lbo, uint32_t sbo, uint32_t swz) {
    return ((uint64_t)(lbo >> 4) << 16) | ((uint64_t)(sbo >> 4) << 32) | ((uint64_t)swz << 62);
}
__device__ __forceinline__ uint64_t mkdesc(uint32_t addr, uint64_t c) { return c | (uint64_t)((addr & 0x3FFFF) >> 4); }
#define WG_FENCE() asm volatile("wgmma.fence.sync.aligned;" ::: "memory")
#define WG_COMMIT() asm volatile("wgmma.commit_group.sync.aligned;" ::: "memory")
#define WG_WAIT(n) asm volatile("wgmma.wait_group.sync.aligned %0;" ::"n"(n) : "memory")
template <int N> __device__ __forceinline__ void reg_fence(float* d) {
#pragma unroll
    for (int i = 0; i < N; i++) asm volatile("" : "+f"(d[i])::"memory");
}
template <int N> __device__ __forceinline__ void reg_def(float* d) {
#pragma unroll
    for (int i = 0; i < N; i++) asm volatile("" : "=f"(d[i]));
}
template <int N> __device__ __forceinline__ void reg_def(uint32_t* d) {
#pragma unroll
    for (int i = 0; i < N; i++) asm volatile("" : "=r"(d[i]));
}
__device__ __forceinline__ bool is_unset(uint4 v) { return min(min(v.x, v.y), min(v.z, v.w)) == 0u; }
__device__ __forceinline__ uint4 nz4(uint32_t a, uint32_t b, uint32_t c, uint32_t d) { return make_uint4(max(a, 1u), max(b, 1u), max(c, 1u), max(d, 1u)); }
__device__ __forceinline__ void wait_flag(const uint32_t* p, uint32_t target) {
    int n = 0;
    while ((int)(ld_relaxed(p) - target) < 0) { if (++n > SPIN_LIMIT) __trap(); }
    asm volatile("fence.acquire.gpu;" ::: "memory");
}
__device__ __forceinline__ float silu_bf(uint32_t cbits) {
    const float c = __uint_as_float(cbits << 16);
    return bf_round(__fdividef(c, 1.f + fminf(ex2(-1.4426950408889634f * c), 1e30f)));
}
__device__ __forceinline__ void gemv_part(uint32_t wmbuf, int npanel, int wp, int lane) {
    const uint32_t wa = wmbuf + wp * 512 + (8 * (lane >> 4) + (lane & 7)) * 32 + ((lane >> 3) & 1) * 16;
    uint2 B[4];
#pragma unroll
    for (int i = 0; i < 4; i++) { const float2 v = lds2f(wmbuf + 28672 + (wp + 8 * i) * 32 + (lane & 3) * 8); B[i] = make_uint2(__float_as_uint(v.x), __float_as_uint(v.y)); }
#pragma unroll 1
    for (int pn = 0; pn < npanel; pn++) {
        float d[4] = {};
        uint32_t A[16];
#pragma unroll
        for (int i = 0; i < 4; i++) ldsm4t(wa + pn * 14336 + (i < 3 || wp < 4 ? i : 0) * 4096, A + 4 * i);
#pragma unroll
        for (int i = 0; i < 4; i++) mma16816(d, A[4 * i], A[4 * i + 1], A[4 * i + 2], A[4 * i + 3], B[i].x, B[i].y);
        if ((lane & 3) == 0) {
            sts1(wmbuf + 29696 + (wp * 32 + pn * 16 + (lane >> 2)) * 4, __float_as_uint(d[0]));
            sts1(wmbuf + 29696 + (wp * 32 + pn * 16 + 8 + (lane >> 2)) * 4, __float_as_uint(d[2]));
        }
    }
}
__device__ __forceinline__ uint32_t slot_off(int l) { return (l < 3 || l > 6 ? l : l == 6 ? 3 : l + 1) * 16384; }
__device__ __forceinline__ void ln_coeffs(float mean, float msq, uint32_t& r2, uint32_t& n2) {
    const float rs = bf_round(rsqrtf(fmaxf(msq - mean * mean, 0.f) + 1e-5f));
    r2 = pack2(rs, rs);
    n2 = pack2(-mean * rs, -mean * rs);
}

template <int sec> __device__ __forceinline__ void ring_loader(const Params& p, uint32_t sb_, int r_, int j_) {
    const uint32_t sb = opaque(sb_);
    const int r = opaque(r_), j = opaque(j_), nq = j >> 1, fs = 4 * (j & 1) + nq;
    const int fa = 224 * fs + ((fs & 1) ? 96 : 0), fb = 224 * fs + ((fs & 1) ? 0 : 128);
#define BAR(i) (sb + M_BAR + 8 * (i))
#define kh (j & 1)
            int sl = 0;
#pragma unroll 1
            for (int s = 0; s < 28; s++) {
                if (s >= 1 && s < 6) mbar_wait(BAR(B_FULL + s - 1), 0);
                const bool pa = s < 14;
                const uint32_t half = pa ? 8192 : 6144;
                mbar_wait(BAR(B_EMPTY + sl), (s >= 7 && s < 14) || s >= 21);
                expect_e(BAR(B_FULL + sl), half);
                tma3_e(sb + slot_off(sl) + sec * half, &p.ga + (pa ? 0 : 2) + sec, 0, 32 * (pa ? s : s - 14), pa ? fa >> 6 : fb >> 5, BAR(B_FULL + sl));
                sl = sl == 6 ? 0 : sl + 1;
            }
            if (!sec) PROFH(3);
#pragma unroll 1
            for (int e = 0; e < 4; e++) {
                const uint32_t dst = sb + slot_off(e) + sec * 8192, bar = BAR(B_FULL + e);
                const int f = (e < 2 ? fa : fb) + 64 * (e & 1) + 32 * sec;
                mbar_wait(BAR(B_EMPTY + e), 0);
                expect_e(bar, e == 3 && sec ? 0 : 8192);
                if (!(e == 3 && sec)) { tma3_e(dst, &p.dn, 112 * nq + 48, f, 0, bar); tma3_e(dst + 4096, &p.dn, 112 * nq, f, 0, bar); }
            }
            sl = 4;
            int e = 4;
#pragma unroll 1
            for (int grp = 0; grp < 6; grp++) {
                const bool pa = grp < 3;
                int sidx = pa ? grp : grp - 3;
                sidx += sidx >= nq;
                const int ofs = 4 * kh + sidx;
                int f = 224 * ofs + ((ofs & 1) ? (pa ? 96 : 0) : (pa ? 0 : 128));
                if (sec && (grp == 0 || grp == 3)) { mbar_wait(BAR(B_HRDY + !pa), 0); fence_async_global(); }
#pragma unroll 1
                for (int k = pa ? 0 : 1; k < 4; k++, e++, f += 32) {
                    const uint32_t dst = sb + slot_off(sl), bar = BAR(B_FULL + sl);
                    mbar_wait(BAR(B_EMPTY + sl), e >= 12 && e < 24);
                    expect_e(bar, 8192);
                    if (!sec) { tma3_e(dst, &p.dn, 112 * nq + 48, f, 0, bar); tma3_e(dst + 4096, &p.dn, 112 * nq, f, 0, bar); }
                    else bulk_e(dst + 8192, g_h2 + (size_t)r * (224 * 512) + f * 64, 8192, bar);
                    sl = sl == 11 ? 0 : sl + 1;
                }
            }
            if (!sec) PROFH(4);
}

__global__ void __cluster_dims__(2, 1, 1) __launch_bounds__(384, 1) fused_block_kernel(const __grid_constant__ Params p) {
    extern __shared__ __align__(1024) unsigned char smem[];
    const uint32_t sb = (uint32_t)__cvta_generic_to_shared(smem);
    const int tid = threadIdx.x, lane = tid & 31, warp = __shfl_sync(~0u, tid >> 5, 0);
    const int m = blockIdx.x >> 1;
    int r, nq;
    {
        int g, i;
        if (m < MAP_S) { g = m < 4 ? 15 : 16; i = m & 3; }
        else if (m < MAP_S + 32) { g = (m - MAP_S) & 7; i = (m - MAP_S) >> 3; }
        else if (m < MAP_S + 60) { i = (m - MAP_S - 32) / 7; g = 8 + (m - MAP_S - 32) - 7 * i; }
        else { g = 16; i = m & 3; }
        r = g; nq = i;
    }
    const int j = opaque(2 * nq + (blockIdx.x & 1)), b = 8 * r + j, fs = 4 * kh + nq;
    const uint32_t sc = r == 16;
    if (lane == 0 && warp < 9 && warp != 6 && warp != 7) {
        const int i0 = warp == 8 ? 0 : 8 + 8 * warp, cnt = warp == 0 || warp == 8 ? 1 : warp < 3 ? 2 : 8;
#pragma unroll
        for (int k = 0; k < 8; k++) if (i0 + k != B_WMFULL) mbar_init(BAR(i0 + k), cnt);
        asm volatile("fence.mbarrier_init.release.cluster;" ::: "memory");
        fence_async_smem();
    }

    if (warp < 8) {
        const int w = warp >> 2, wi = warp & 3;
#define COORDS const int t = fresh_tid() & 127, lane = t & 31, q = lane & 3, lr = lane >> 2, ra = 64 * w + 16 * wi + lr; \
        const uint32_t lx = (lane >> 4) ^ (lane & 7), mrow = (64 * w + 16 * wi + ((lane >> 3) & 1) * 8 + (lane & 7)) * 128; \
        (void)q; (void)lr; (void)ra; (void)lx; (void)mrow;
        const int sid = 2 * (j & 3) + w;
#define RUN(k) (!sc || sid == (k))
#define WAIT(i, par) mbar_wait(BAR(i), (par) | sc)
        constexpr uint64_t DB128 = dconst(4096, 1024, 1);
        bar_arrive(9, 384);
        bar_sync(0, 384);
        asm volatile("barrier.cluster.arrive.relaxed.aligned;" ::: "memory");
        asm volatile("setmaxnreg.inc.sync.aligned.u32 224;");
        PROFC(0);
        uint32_t xr[16];
        {
            COORDS
            uint32_t h[112];
            if (RUN(0)) {
                float ds[4] = {}, da[2][4] = {}, db[2][4] = {};
                const uint32_t ONE2 = 0x3F803F80u;
                if (kh == 0) { WAIT(B_WMFULL, 0); gemv_part(sb + OFF_Y + HALF, 1, warp, lane); warp_arrive(BAR(B_GEMV)); }
#pragma unroll
                for (int kb = 0; kb < 7; kb++) {
                    WAIT(B_XFULL + kb, 0);
#pragma unroll
                    for (int k4 = 0; k4 < 4; k4++) ldsm4(sb + OFF_X + mrow + kb * 16384 + (((2 * k4) ^ lx) << 4), h + 16 * kb + 4 * k4);
#pragma unroll
                    for (int k4 = 0; k4 < 4; k4++) {
                        const uint32_t* f = h + 16 * kb + 4 * k4;
                        mma16816(ds, f[0], f[1], f[2], f[3], ONE2, ONE2);
                        mma1688(da[0], f[0], f[1], f[0]); mma1688(db[0], f[0], f[1], f[1]);
                        mma1688(da[1], f[2], f[3], f[2]); mma1688(db[1], f[2], f[3], f[3]);
                    }
                }
#pragma unroll
                for (int i = 0; i < 4; i++) {
                    const int ch = 7 * j + 2 * i + (lane >> 4);
                    ldsm4(sb + OFF_X + mrow + (ch >> 3) * 16384 + (((ch ^ lane) & 7) << 4), xr + 4 * i);
                }
                warp_arrive(BAR(B_XFREE));
                PROFC(27);
                float qa = (lr & 1) ? da[0][1] + da[1][1] : da[0][0] + da[1][0];
                float qb = (lr & 1) ? db[0][3] + db[1][3] : db[0][2] + db[1][2];
                const int src = (lane & ~3) | (lr >> 1);
                qa = __shfl_sync(~0u, qa, src);
                qb = __shfl_sync(~0u, qb, src);
                uint32_t ra2, na2, rb2, nb2;
                ln_coeffs(ds[0] * (1.f / DM), qa * (1.f / DM), ra2, na2);
                ln_coeffs(ds[2] * (1.f / DM), qb * (1.f / DM), rb2, nb2);
#pragma unroll
                for (int i = 0; i < 112; i += 2) { h[i] = hfma2(h[i], ra2, na2); h[i + 1] = hfma2(h[i + 1], rb2, nb2); }
                if (kh == 1) { WAIT(B_WMFULL, 0); gemv_part(sb + OFF_Y + HALF, 2, warp, lane); warp_arrive(BAR(B_GEMV)); }
            } else { reg_def<112>(h); reg_def<16>(xr); }
            PROFC(1);
            if (RUN(1)) {
                float ak[28], av[28], aq[28];
                uint32_t kp[14], vp[14];
                const uint64_t bk0 = mkdesc(sb + OFF_Y, DB128) + kh, bv0 = mkdesc(sb + OFF_Y + HALF, DB128) + kh, bq0 = mkdesc(sb + OFF_X, DB128) + kh;
                uint32_t* kvg = g_kv + (size_t)(b * 2) * 3584 + (8 * w + 2 * wi) * 224 + lane;
                WAIT(B_FULLK, 0);
                WAIT(B_MOD1, 0);
                PROFC(2);
                reg_def<28>(ak);
#pragma unroll
                for (int g4 = 0; g4 < 4; g4++) {
#pragma unroll
                    for (int ks = 7 * g4; ks < 7 * g4 + 7; ks++) {
                        const uint4 st = *(const uint4*)(smem + M_ST + ks * 64 + q * 16);
                        h[4 * ks] = hfma2(h[4 * ks], st.x, st.y); h[4 * ks + 1] = hfma2(h[4 * ks + 1], st.x, st.y);
                        h[4 * ks + 2] = hfma2(h[4 * ks + 2], st.z, st.w); h[4 * ks + 3] = hfma2(h[4 * ks + 3], st.z, st.w);
                    }
                    WG_FENCE();
#pragma unroll
                    for (int ks = 7 * g4; ks < 7 * g4 + 7; ks++) wgmma_rs_56<1>(ak, h[4 * ks], h[4 * ks + 1], h[4 * ks + 2], h[4 * ks + 3], bk0 + ks * 128, ks != 0);
                }
                WG_COMMIT();
                PROFC(3);
                WAIT(B_FULLV, 0);
                reg_def<28>(av);
                WG_FENCE();
#pragma unroll
                for (int ks = 0; ks < 8; ks++) wgmma_rs_56<1>(av, h[4 * ks], h[4 * ks + 1], h[4 * ks + 2], h[4 * ks + 3], bv0 + ks * 128, ks != 0);
                WG_COMMIT();
                WG_WAIT(1);
                reg_fence<28>(ak);
#pragma unroll
                for (int g = 0; g < 7; g++) {
                    kp[2 * g] = pack2(ak[4 * g], ak[4 * g + 1]); kp[2 * g + 1] = pack2(ak[4 * g + 2], ak[4 * g + 3]);
                    kvg[g * 32] = kp[2 * g]; kvg[224 + g * 32] = kp[2 * g + 1];
                }
                warp_arrive(BAR(B_PUB));
                PROFC(4);
                WG_FENCE();
#pragma unroll
                for (int ks = 8; ks < 28; ks++) wgmma_rs_56<1>(av, h[4 * ks], h[4 * ks + 1], h[4 * ks + 2], h[4 * ks + 3], bv0 + ks * 128, 1);
                WG_COMMIT();
                WAIT(B_FULLQ, 0);
                reg_def<28>(aq);
                WG_FENCE();
#pragma unroll
                for (int ks = 0; ks < 8; ks++) wgmma_rs_56<1>(aq, h[4 * ks], h[4 * ks + 1], h[4 * ks + 2], h[4 * ks + 3], bq0 + ks * 128, ks != 0);
                WG_COMMIT();
                WG_WAIT(1);
                reg_fence<28>(av);
#pragma unroll
                for (int g = 0; g < 7; g++) {
                    vp[2 * g] = pack2(av[4 * g], av[4 * g + 1]); vp[2 * g + 1] = pack2(av[4 * g + 2], av[4 * g + 3]);
                    kvg[3584 + g * 32] = vp[2 * g]; kvg[3584 + 224 + g * 32] = vp[2 * g + 1];
                }
                warp_arrive(BAR(B_PUB + 1));
                PROFC(5);
                WG_FENCE();
#pragma unroll
                for (int ks = 8; ks < 28; ks++) wgmma_rs_56<1>(aq, h[4 * ks], h[4 * ks + 1], h[4 * ks + 2], h[4 * ks + 3], bq0 + ks * 128, 1);
                WG_COMMIT();
                WAIT(B_PUB + 1, 0);
                const uint32_t ko = sb + OFF_Y + Y_KOWN + (8 * w + 2 * wi) * 896 + lane * 4;
                const uint32_t qo = sb + OFF_Y + Y_Q + (8 * w + 2 * wi) * 1024 + lane * 4;
#pragma unroll
                for (int g = 0; g < 7; g++) {
                    sts1(ko + g * 128, kp[2 * g]); sts1(ko + 896 + g * 128, kp[2 * g + 1]);
                    sts1(ko + (Y_VOWN - Y_KOWN) + g * 128, vp[2 * g]); sts1(ko + (Y_VOWN - Y_KOWN) + 896 + g * 128, vp[2 * g + 1]);
                }
                WG_WAIT(0);
                reg_fence<28>(aq);
                __syncwarp();
                if (lane < 3 && w == 1) mbar_arrive(BAR(B_EMPTY + lane));
#pragma unroll
                for (int g = 0; g < 7; g++) {
                    const uint32_t q0 = pack2(aq[4 * g], aq[4 * g + 1]), q1 = pack2(aq[4 * g + 2], aq[4 * g + 3]);
                    if (g == 3) {
                        sts1(qo + 3 * 128, q < 2 ? q0 : 0u); sts1(qo + 1024 + 3 * 128, q < 2 ? q1 : 0u);
                        sts1(qo + 4 * 128, q < 2 ? 0u : q0); sts1(qo + 1024 + 4 * 128, q < 2 ? 0u : q1);
                    } else {
                        const int ch = g < 3 ? g : g + 1;
                        sts1(qo + ch * 128, q0); sts1(qo + 1024 + ch * 128, q1);
                    }
                }
                if (!sc) bar_sync(3, 256);
            }
        }
        PROFC(6);
        WAIT(B_KRFULL, 0);
        PROFC(7);
        if (RUN(2)) {
#pragma unroll 1
            for (int hf = sc; hf < 2; hf++) {
                COORDS
                float s[136];
                float na = 0.f, nb = 0.f;
                const float CS = 0.18898223650461361f * 1.4426950408889634f;
                const int kg0 = 8 * hf + 2 * wi;
                const int pmin = 16 - 8 * r - 4 * hf - wi;
                const float NEG = __int_as_float(0xFF800000);
                {
                    uint32_t F[8];
                    const uint32_t qa = sb + OFF_Y + Y_Q + (kg0 + ((lane >> 3) & 1)) * 1024 + (4 * w + (lane >> 4)) * 128 + (lane & 7) * 16;
                    ldsm4(qa, F); ldsm4(qa + 256, F + 4);
                    uint32_t ka = sb + OFF_Y + Y_K + kg0 * 896 + (3 * w + (lane >> 3)) * 128 + (lane & 7) * 16;
#pragma unroll
                    for (int g = 0; g < 34; g++) {
                        uint32_t B[4];
                        if (g >= 12 && g % 4 == 0) ka += __float_as_uint(s[4 * (g - 12)]) & p.zero;
                        ldsm4(ka + g * 896, B);
                        mma16816_first(s + 4 * g, F[0], F[1], F[2], F[3], B[0], B[1]);
                        mma16816_v(s + 4 * g, F[4], F[5], F[6], F[7], B[2], B[3]);
                    }
                    const bool c0 = 2 * q > lr, c1 = 2 * q + 1 > lr;
                    if (!c0) { s[0] = NEG; s[6] = NEG; }
                    if (!c1) { s[1] = NEG; s[7] = NEG; }
                    s[2] = NEG; s[3] = NEG;
                    if (c0) { s[128] = NEG; s[134] = NEG; }
                    if (c1) { s[129] = NEG; s[135] = NEG; }
                    s[132] = NEG; s[133] = NEG;
                    float ma = NEG, mb = NEG;
#pragma unroll
                    for (int pp = 0; pp < 17; pp++) {
                        const float* e = s + 8 * pp;
                        const float bias = pp < pmin ? NEG : 0.f;
                        ma = fmaxf(ma, fmaxf(fmaxf(e[0], e[1]), fmaxf(e[4], e[5])) + bias);
                        mb = fmaxf(mb, fmaxf(fmaxf(e[2], e[3]), fmaxf(e[6], e[7])) + bias);
                    }
                    ma = fmaxf(ma, __shfl_xor_sync(~0u, ma, 1)); mb = fmaxf(mb, __shfl_xor_sync(~0u, mb, 1));
                    ma = fmaxf(ma, __shfl_xor_sync(~0u, ma, 2)); mb = fmaxf(mb, __shfl_xor_sync(~0u, mb, 2));
                    na = -ma * CS; nb = -mb * CS;
                }
                PROFC(8 + 3 * hf);
                {
                    if (hf == 0) mbar_wait(BAR(B_VRFULL), 0);
                    float o[16] = {}, rs[4] = {};
                    const uint32_t va = sb + OFF_Y + Y_VR + (kg0 + ((lane >> 3) & 1)) * 896 + (3 * w + (lane >> 4)) * 128 + (lane & 7) * 16;
#pragma unroll
                    for (int pp = 0; pp < 17; pp++) {
                        uint32_t B[8];
                        const uint32_t v = va + pp * 1792 + (pp == 16 || (pp >= 9 && kg0 + 2 * pp >= 32) ? Y_VOWN - 32 * 896 : 0);
                        ldsm4t(v, B); ldsm4t(v + 256, B + 4);
                        float e[8];
#pragma unroll
                        for (int i = 0; i < 8; i++) e[i] = ex2(fmaf(s[8 * pp + i], CS, ((i & 2) ? nb : na) + (pp < pmin ? NEG : 0.f)));
                        const uint32_t p0 = pack2(e[0], e[1]), p1 = pack2(e[2], e[3]), p2 = pack2(e[4], e[5]), p3 = pack2(e[6], e[7]);
                        mma16816(rs, p0, p1, p2, p3, 0x3F803F80u, 0x3F803F80u);
#pragma unroll
                        for (int g = 0; g < 4; g++) mma16816(o + 4 * g, p0, p1, p2, p3, B[2 * g], B[2 * g + 1]);
                    }
                    PROFC(9 + 3 * hf);
                    const float ia = rcp(rs[0]), ib = rcp(rs[2]);
                    uint32_t* og = g_o + (size_t)(2 * r + hf) * 14336 + (7 * j + 3 * w) * 256 + wi * 64 + lane;
#pragma unroll
                    for (int g = 0; g < 4; g++) {
                        if ((g == 3 - 3 * w) ? ((q >> 1) == w) : true) {
                            og[g * 256] = pack2(o[4 * g] * ia, o[4 * g + 1] * ia);
                            og[g * 256 + 32] = pack2(o[4 * g + 2] * ib, o[4 * g + 3] * ib);
                        }
                    }
                    warp_arrive(BAR(B_PUB + 2 + hf));
                    PROFC(10 + 3 * hf);
                }
            }
        }
        uint32_t x1p[14];
        COORDS
        constexpr uint64_t DT = dconst(1024, 128, 0);
        if (RUN(4)) {
            float ac[28];
            const uint64_t ad = mkdesc(sb + (w ? OFF_Y + HALF : OFF_X), DT), bd = mkdesc(sb + OFF_X + HALF, DB128) + kh;
            WAIT(B_WOFULL, 0);
            WAIT(B_MOD2, 0);
            WAIT(B_GFULL + w, 0);
            PROFC(28);
            reg_def<28>(ac);
#pragma unroll 1
            for (int u = 0; u < 4; u++) {
                WG_FENCE();
#pragma unroll
                for (int i = 0; i < 7; i++) wgmma_ss_56<1>(ac, ad + (7 * u + i) * 128, bd + (7 * u + i) * 128, (u | i) != 0);
            }
            WG_COMMIT();
            WG_WAIT(0);
            reg_fence<28>(ac);
            PROFC(14);
            __syncwarp();
            if (lane < 3) mbar_arrive(BAR(B_EMPTY + 3 + lane));
            if (lane < 3 && w == 0) mbar_arrive(BAR(B_EMPTY + lane));
            float s1a = 0.f, s2a = 0.f, s1b = 0.f, s2b = 0.f;
            uint32_t* xo = g_x1 + (size_t)(2 * r + w) * 14336 + 7 * j * 256 + wi * 64 + lane;
#pragma unroll
            for (int g = 0; g < 7; g++) {
                const float2 ga = *(const float2*)(smem + M_G + (8 * g + 2 * q) * 4);
                x1p[2 * g] = pack2(fmaf(ga.x, ac[4 * g], bf_lo(xr[2 * g])), fmaf(ga.y, ac[4 * g + 1], bf_hi(xr[2 * g])));
                x1p[2 * g + 1] = pack2(fmaf(ga.x, ac[4 * g + 2], bf_lo(xr[2 * g + 1])), fmaf(ga.y, ac[4 * g + 3], bf_hi(xr[2 * g + 1])));
                xo[g * 256] = x1p[2 * g]; xo[g * 256 + 32] = x1p[2 * g + 1];
                const float u0 = bf_lo(x1p[2 * g]), u1 = bf_hi(x1p[2 * g]), u2 = bf_lo(x1p[2 * g + 1]), u3 = bf_hi(x1p[2 * g + 1]);
                s1a += u0 + u1; s2a += u0 * u0 + u1 * u1; s1b += u2 + u3; s2b += u2 * u2 + u3 * u3;
            }
            float ka = (q & 1) ? s2a : s1a, kb2 = (q & 1) ? s2b : s1b;
            ka += __shfl_xor_sync(~0u, (q & 1) ? s1a : s2a, 1); kb2 += __shfl_xor_sync(~0u, (q & 1) ? s1b : s2b, 1);
            const float kk = ((q & 2) ? kb2 : ka) + __shfl_xor_sync(~0u, (q & 2) ? ka : kb2, 2);
            ((float*)g_st)[(((2 * r + w) * 8 + j) * 64 + 16 * wi + lr + 4 * (q & 2)) * 2 + (q & 1)] = kk;
            __syncwarp();
            if (lane < 2) mbar_arrive(BAR(B_PUB + 4 + w));
        } else reg_def<14>(x1p);
        PROFC(15);
        uint32_t h2a[32], h2b[24];
        if (RUN(6)) {
            const int fa = 224 * fs + ((fs & 1) ? 96 : 0), fb = 224 * fs + ((fs & 1) ? 0 : 128);
            uint32_t* h2g = g_h2 + (size_t)r * (224 * 512) + (8 * w + 2 * wi) * 32 + lane;
            const uint64_t a0 = mkdesc(sb + OFF_Y + w * HALF, DT);
            const int s0 = sc ? 12 : 0;
            {
                WAIT(B_GFULL + 2 + w, 0);
                PROFC(16);
                float2 sa = make_float2(0.f, 0.f), sbb = sa;
#pragma unroll
                for (int jj = 0; jj < 8; jj++) {
                    const float2 u = lds2f(sb + OFF_X + X_STAT + w * 4096 + (jj * 64 + 16 * wi + lr) * 8), v = lds2f(sb + OFF_X + X_STAT + w * 4096 + (jj * 64 + 16 * wi + lr + 8) * 8);
                    sa.x += u.x; sa.y += u.y; sbb.x += v.x; sbb.y += v.y;
                }
                warp_arrive(BAR(B_EMPTY + 6));
                uint32_t ra2, na2, rb2, nb2;
                ln_coeffs(sa.x * (1.f / DM), sa.y * (1.f / DM), ra2, na2);
                ln_coeffs(sbb.x * (1.f / DM), sbb.y * (1.f / DM), rb2, nb2);
                const uint32_t ha = sb + OFF_Y + w * HALF + (lane >> 4) * 1024 + (2 * wi + ((lane >> 3) & 1)) * 128 + (lane & 7) * 16;
                const uint32_t sta = sb + M_ST + q * 16;
                auto prep = [&](int s, uint32_t* f) {
#pragma unroll
                    for (int i = 0; i < 2; i++) {
                        uint32_t x[4];
                        ldsm4(ha + (2 * s + i) * 2048, x);
                        const uint4 st = lds4(sta + (2 * s + i) * 64);
                        f[4 * i] = hfma2(hfma2(x[0], ra2, na2), st.x, st.y); f[4 * i + 1] = hfma2(hfma2(x[1], rb2, nb2), st.x, st.y);
                        f[4 * i + 2] = hfma2(hfma2(x[2], ra2, na2), st.z, st.w); f[4 * i + 3] = hfma2(hfma2(x[3], rb2, nb2), st.z, st.w);
                        stsm4(ha + (2 * s + i) * 2048, f[4 * i], f[4 * i + 1], f[4 * i + 2], f[4 * i + 3]);
                    }
                };
                float ac[128];
                uint32_t fr[2][8];
                reg_def<128>(ac);
                prep(s0, fr[0]);
                PROFC(17);
                int sl = 0, prev = 0;
#pragma unroll 1
                for (int s2 = s0; s2 < 14; s2 += 2) {
#pragma unroll
                    for (int e = 0; e < 2; e++) {
                        const int s = s2 + e;
                        const uint32_t* f = fr[e];
                        WAIT(B_FULL + sl, s >= 7);
                        const uint64_t bd = mkdesc(sb + slot_off(sl), DB128);
                        WG_FENCE();
                        wgmma_rs_256<1>(ac, f[0], f[1], f[2], f[3], bd, s != 0);
                        wgmma_rs_256<1>(ac, f[4], f[5], f[6], f[7], bd + 128, 1);
                        WG_COMMIT();
                        WG_WAIT(1);
                        if (s > 0) warp_arrive(BAR(B_EMPTY + prev));
                        if (s < 13) prep(s + 1, fr[e ^ 1]);
                        prev = sl; sl = sl == 6 ? 0 : sl + 1;
                    }
                }
                fence_async_smem();
                WG_WAIT(0);
                reg_fence<128>(ac);
                warp_arrive(BAR(B_EMPTY + 6));
                PROFC(18);
#pragma unroll
                for (int g = 0; g < 16; g++) {
                    h2a[2 * g] = hmul2(pack2_relu(ac[4 * g], ac[4 * g + 1]), pack2(ac[64 + 4 * g], ac[64 + 4 * g + 1]));
                    h2a[2 * g + 1] = hmul2(pack2_relu(ac[4 * g + 2], ac[4 * g + 3]), pack2(ac[64 + 4 * g + 2], ac[64 + 4 * g + 3]));
                    h2g[(fa / 8 + g) * 512] = h2a[2 * g]; h2g[(fa / 8 + g) * 512 + 32] = h2a[2 * g + 1];
                }
                warp_arrive(BAR(B_PUB + 6));
                bar_sync(1 + w, 128);
            }
            PROFC(19);
            {
                float ac[96];
                reg_def<96>(ac);
                int sl = 0, prev = 0;
#pragma unroll 1
                for (int s = s0; s < 14; s++) {
                    WAIT(B_FULL + sl, s >= 7);
                    const uint64_t ad = a0 + s * 256, bd = mkdesc(sb + slot_off(sl), dconst(2048, 512, 2));
                    WG_FENCE();
                    wgmma_ss_192<1>(ac, ad, bd, s != 0);
                    wgmma_ss_192<1>(ac, ad + 128, bd + 64, 1);
                    WG_COMMIT();
                    if (s > 0) { WG_WAIT(1); warp_arrive(BAR(B_EMPTY + prev)); }
                    prev = sl; sl = sl == 6 ? 0 : sl + 1;
                }
                WG_WAIT(0);
                reg_fence<96>(ac);
                __syncwarp();
                if (lane < 6) mbar_arrive(BAR(B_EMPTY + 6 + lane));
                asm volatile("barrier.cluster.wait.aligned;" ::: "memory");
                if (lane == 0 && !sc) {
                    uint32_t rb;
                    asm volatile("mapa.shared::cluster.u32 %0, %1, %2;" : "=r"(rb) : "r"(BAR(B_PEER)), "r"(kh ^ 1));
                    asm volatile("mbarrier.arrive.relaxed.cluster.shared::cluster.b64 _, [%0];" ::"r"(rb) : "memory");
                }
                PROFC(20);
#pragma unroll
                for (int g = 0; g < 12; g++) {
                    h2b[2 * g] = hmul2(pack2_relu(ac[4 * g], ac[4 * g + 1]), pack2(ac[48 + 4 * g], ac[48 + 4 * g + 1]));
                    h2b[2 * g + 1] = hmul2(pack2_relu(ac[4 * g + 2], ac[4 * g + 3]), pack2(ac[48 + 4 * g + 2], ac[48 + 4 * g + 3]));
                    h2g[(fb / 8 + g) * 512] = h2b[2 * g]; h2g[(fb / 8 + g) * 512 + 32] = h2b[2 * g + 1];
                }
                warp_arrive(BAR(B_PUB + 7));
            }
        } else { reg_def<32>(h2a); reg_def<24>(h2b); }
        PROFC(21);
        if (RUN(7)) {
            float ac[56];
            reg_def<56>(ac);
            constexpr uint64_t DAN = dconst(2048, 128, 0);
#pragma unroll
            for (int e = 0; e < 4; e++) {
                WAIT(B_FULL + e, 0);
                const uint64_t bd = mkdesc(sb + slot_off(e), DB128);
                const uint32_t* hh = e < 2 ? h2a + 16 * e : h2b + 16 * (e - 2);
                WG_FENCE();
#pragma unroll
                for (int k = 0; k < (e < 3 ? 4 : 2); k++) wgmma_rs_112<1>(ac, hh[4 * k], hh[4 * k + 1], hh[4 * k + 2], hh[4 * k + 3], bd + (k >> 1) * 512 + (k & 1) * 128, (e | k) != 0);
                WG_COMMIT();
                if (e > 0) { WG_WAIT(1); warp_arrive(BAR(B_EMPTY + e - 1)); }
            }
            PROFC(22);
            int sl = 4, prev = 3;
#pragma unroll 1
            for (int e = 4; e < 25; e++) {
                WAIT(B_FULL + sl, e >= 12 && e < 24);
                if (e == 16) PROFC(23);
                const uint32_t sa = sb + slot_off(sl);
                const uint64_t ad = mkdesc(sa + 8192 + w * 1024, DAN), bd = mkdesc(sa, DB128);
                WG_FENCE();
                wgmma_ss_112<1>(ac, ad, bd, 1);
                wgmma_ss_112<1>(ac, ad + 256, bd + 128, 1);
                WG_COMMIT();
                if (e < 14) { WG_WAIT(1); warp_arrive(BAR(B_EMPTY + prev)); }
                prev = sl; sl = sl == 11 ? 0 : sl + 1;
            }
            mbar_wait_cluster(BAR(B_PEER), sc);
            WG_WAIT(0);
            reg_fence<56>(ac);
            PROFC(24);
            uint32_t rdst, rbar;
            asm volatile("mapa.shared::cluster.u32 %0, %1, %2;" : "=r"(rdst) : "r"(sb + OFF_Y + (5 + w) * 16384 + t * 16), "r"(kh ^ 1 ^ sc));
            asm volatile("mapa.shared::cluster.u32 %0, %1, %2;" : "=r"(rbar) : "r"(BAR(B_XCH + w)), "r"(kh ^ 1 ^ sc));
#define ACG(g, i) ac[4 * (((g) + 8) % 14) + (i)]
#pragma unroll
            for (int g = 0; g < 7; g++) {
                const float v0 = kh ? ACG(g, 0) : ACG(g + 7, 0), v1 = kh ? ACG(g, 1) : ACG(g + 7, 1);
                const float v2 = kh ? ACG(g, 2) : ACG(g + 7, 2), v3 = kh ? ACG(g, 3) : ACG(g + 7, 3);
                if (!sc) asm volatile("st.async.shared::cluster.mbarrier::complete_tx::bytes.v4.f32 [%0], {%1,%2,%3,%4}, [%5];"
                             ::"r"(rdst + g * 2048), "f"(v0), "f"(v1), "f"(v2), "f"(v3), "r"(rbar) : "memory");
            }
            mbar_wait_cluster(BAR(B_XCH + w), sc);
            PROFC(25);
            bf16* og = (sc ? (bf16*)(g_h2 + 16 * 224 * 512) : p.out + (size_t)128 * r * DM) + (size_t)ra * DM + 56 * j + 2 * q;
#pragma unroll
            for (int g = 0; g < 7; g++) {
                const uint4 rv = *(const uint4*)(smem + OFF_Y + (5 + w) * 16384 + t * 16 + g * 2048);
                const float2 gb = *(const float2*)(smem + M_G + 224 + (8 * g + 2 * q) * 4);
                const float v0 = (kh ? ACG(g + 7, 0) : ACG(g, 0)) + __uint_as_float(rv.x), v1 = (kh ? ACG(g + 7, 1) : ACG(g, 1)) + __uint_as_float(rv.y);
                const float v2 = (kh ? ACG(g + 7, 2) : ACG(g, 2)) + __uint_as_float(rv.z), v3 = (kh ? ACG(g + 7, 3) : ACG(g, 3)) + __uint_as_float(rv.w);
                *(uint32_t*)(og + 8 * g) = pack2(fmaf(gb.x, v0, bf_lo(x1p[2 * g])), fmaf(gb.y, v1, bf_hi(x1p[2 * g])));
                *(uint32_t*)(og + 8 * DM + 8 * g) = pack2(fmaf(gb.x, v2, bf_lo(x1p[2 * g + 1])), fmaf(gb.y, v3, bf_hi(x1p[2 * g + 1])));
            }
        }
        PROFC(26);
        warp_arrive(BAR(B_DONE));
    } else {
        const int lane = fresh_tid() & 31;
        const bool early = kh == 0, gemv = r < 14;
        const int mcol = early ? 16 * (4 * r + nq) : 2 * DM + 32 * (4 * r + nq);
        const uint32_t wmbuf = sb + OFF_Y + HALF;
        asm volatile("setmaxnreg.dec.sync.aligned.u32 56;");
        if (warp == 9) {
#pragma unroll
            for (int i = 56; i < 63; i++) init_e(BAR(i), 1);
            fence_async_smem();
        }
        if (warp == 8) { init_e(BAR(B_WMFULL), 2); fence_async_smem(); }
        bar_arrive(0, 384);
        asm volatile("barrier.cluster.arrive.relaxed.aligned;" ::: "memory");
        uint32_t target = 0;
        if (warp == 8) {
            if (!sc) {
                expect_e(BAR(B_WMFULL), gemv ? 28672 >> early : 0);
                if (early && gemv) { tma3_e(wmbuf, &p.wm, mcol, 0, 0, BAR(B_WMFULL)); tma3_e(wmbuf + 7168, &p.wm, mcol, 224, 0, BAR(B_WMFULL)); }
#pragma unroll 1
                for (int kb = 0; kb < 7; kb++) {
                    expect_e(BAR(B_XFULL + kb), 16384);
                    tma3_e(sb + OFF_X + kb * 16384, &p.xm, 64 * kb, 128 * r, 0, BAR(B_XFULL + kb));
                }
            }
#pragma unroll 1
            for (int mt = 0; mt < 4; mt++) {
                if (mt == 1) {
                    if (!early && gemv) {
#pragma unroll 1
                        for (int k = 0; k < 4; k++) tma3_e(wmbuf + k * 7168, &p.wm, mcol + (k >> 1) * 16, (k & 1) * 224, 0, BAR(B_WMFULL));
                    }
                    bar_sync(9, 384);
                    if (sc) return;
                    mbar_wait(BAR(B_MOD1), 0);
                    mbar_wait(BAR(B_WMFREE), 0);
                }
                if (mt == 2) mbar_wait(BAR(B_XFREE), 0);
                if (mt == 3) mbar_wait(BAR(B_VRFULL), 0);
                const uint32_t bar = BAR(mt == 3 ? B_WOFULL : B_FULLK + mt), dst = sb + (mt < 2 ? OFF_Y : OFF_X) + (mt & 1) * HALF;
                const int c0 = (mt < 2 ? DM + DM * mt : 0) + 56 * j - 8 * kh;
                if (!sc) {
                    expect_e(bar, HALF);
                    tma3_e(dst, mt == 3 ? &p.wo : &p.qkv, c0, 0, 0, bar);
                    tma3_e(dst + HALF / 2, mt == 3 ? &p.wo : &p.qkv, c0, 224, 0, bar);
                }
            }
            expect_e(BAR(B_XCH), 14336);
            expect_e(BAR(B_XCH + 1), 14336);
        } else {
            if (warp == 10 && !sc) {
                l2_prefetch_e((const char*)p.wqkv + (size_t)b * 9408, 9408);
                if (lane == 0) sts1(sb + M_EPOCH, atomicAdd(&g_ticket, 1u) / NCTA);
            }
            if (warp == 11) {
#pragma unroll
                for (int i = 0; i < 8; i++) {
                    const int wd = lane + 32 * i;
                    const uint32_t cb = i < 7 ? __ldg((const uint32_t*)p.c + wd) : 0u;
                    sts1(wmbuf + 28672 + (wd >> 3) * 32 + (wd & 3) * 8 + (wd & 4), pack2(silu_bf(cb & 0xFFFFu), silu_bf(cb >> 16)));
                }
            }
            bar_sync(9, 384);
            if (sc) return;
            target = lds1(sb + M_EPOCH) + 1;
            const uint32_t tag = target & 0xFFFFu;
            if (warp == 11) {
                warp_arrive(BAR(B_WMFULL));
                mbar_wait(BAR(B_GEMV), 0);
                float sum = 0.f;
#pragma unroll
                for (int i = 0; i < 8; i++) sum += *(const float*)(smem + OFF_Y + HALF + 29696 + (i * 32 + (early ? lane & 15 : lane)) * 4);
                const uint32_t word = (pack2(sum, 0.f) << 16) | tag;
                if (gemv) {
                    uint32_t* mg = g_mod + mcol + (early ? (lane & 15) + (lane >> 4) * 4 * 6 * DM : lane);
#pragma unroll
                    for (int i = 0; i < 8; i++) if (i < 4 || !early) st_relaxed(mg + i * 6 * DM, word);
                }
                warp_arrive(BAR(B_WMFREE));
            }
            const uint4* modp = (const uint4*)g_mod + (r & 7) * (6 * DM / 4);
            const bool p2 = warp == 11;
            mbar_wait(BAR(p2 ? B_PUB : B_XFULL + 4), 0);
#pragma unroll 1
            for (int it = p2 ? 0 : warp - 9; it < (p2 ? 2 : warp - 8); it++) {
                const int i0 = lane + 32 * it, imax = p2 ? 251 : 223;
                uint4 v[4];
#pragma unroll 1
                for (int n = 0;; n++) {
                    uint32_t bad = 0;
#pragma unroll
                    for (int k = 0; k < 4; k++) {
                        const int i = min(i0 + 64 * k, imax);
                        v[k] = ld_relaxed4(modp + (i < 224 ? (p2 ? 336 : 0) + i : (i < 238 ? 14 * j + i : 14 * j + i + 322)));
                        bad |= (v[k].x ^ tag) | (v[k].y ^ tag) | (v[k].z ^ tag) | (v[k].w ^ tag);
                    }
                    if (!__any_sync(~0u, bad & 0xFFFFu)) break;
                    if (n > SPIN_LIMIT) __trap();
                }
#pragma unroll
                for (int k = 0; k < 4; k++) {
                    const int i = min(i0 + 64 * k, imax);
                    if (i < 224) {
                        const int isc = i >= 112, c4 = i - 112 * isc;
                        const float one = isc ? 1.f : 0.f;
                        const uint32_t a = sb + M_ST + (c4 >> 2) * 64 + (c4 & 1) * 32 + (c4 & 2) * 4 + (isc ? 0 : 4);
                        sts1(a, pack2(bf_hi(v[k].x) + one, bf_hi(v[k].y) + one));
                        sts1(a + 16, pack2(bf_hi(v[k].z) + one, bf_hi(v[k].w) + one));
                    } else {
                        sts4(sb + M_G + (i - 224) * 16, make_uint4(v[k].x & 0xFFFF0000u, v[k].y & 0xFFFF0000u, v[k].z & 0xFFFF0000u, v[k].w & 0xFFFF0000u));
                    }
                }
                warp_arrive(BAR(p2 ? B_MOD2 : B_MOD1));
            }
            if (warp == 9) {
#pragma unroll 1
                for (int kv = 0; kv < 2; kv++) {
                    mbar_wait(BAR(B_PUB + kv), 0);
                    if (lane >= 1 && lane <= 2 && r >= lane) wait_flag(g_flag + kv * 128 + b - 8 * lane, target);
                    __syncwarp();
                    fence_async_global();
                    const uint32_t dst = sb + OFF_Y + (kv ? Y_VR : Y_K);
                    expect_e(BAR(B_KRFULL + kv), r >= 2 ? 28672 : r == 1 ? 14336 : 0);
                    if (r >= 2) bulk_e(dst, g_kv + (size_t)((b - 16) * 2 + kv) * 3584, 14336, BAR(B_KRFULL + kv));
                    if (r >= 1) bulk_e(dst + 14336, g_kv + (size_t)((b - 8) * 2 + kv) * 3584, 14336, BAR(B_KRFULL + kv));
                }
            } else if (warp == 11) {
                mbar_wait(BAR(B_VRFULL), 0);
                l2_prefetch_e((const char*)p.wg + (size_t)b * 12544, 12544);
                l2_prefetch_e((const char*)p.wu + (size_t)b * 12544, 12544);
                l2_prefetch_e((const char*)p.wd + (size_t)b * 12544, 12544);
            }
        }
        if (warp == 8 || warp == 11) {
            const int sec = warp == 11;
            if (sec) ring_loader<1>(p, sb, r, j); else ring_loader<0>(p, sb, r, j);
            mbar_wait(BAR(B_DONE), 0);
        } else if (warp == 9) {
#pragma unroll
            for (int ev = 0; ev < 4; ev++) expect_e(BAR(B_GFULL + ev), ev < 2 ? HALF : HALF + 4096);
            mbar_wait(BAR(B_PUB + 2), 0);
            const uint32_t* fp = g_flag + (2 + (lane >> 3)) * 128 + 8 * r + (lane & 7);
            const uint32_t* src = g_ox + (size_t)2 * r * 14336;
            const float2* ssrc = g_st + 2 * r * 512;
#pragma unroll 1
            for (int n = 0, ev = 0; ev < 4; n++) {
                if (ev == 1) mbar_wait(BAR(B_PUB + 3), 0);
                uint32_t ok = __ballot_sync(~0u, (int)(ld_relaxed(fp) - target) >= 0) >> (8 * ev);
                while ((ok & 0xFFu) == 0xFFu) {
                    asm volatile("fence.acquire.gpu;" ::: "memory");
                    fence_async_global();
                    const uint32_t bar = BAR(B_GFULL + ev);
                    bulk_e(sb + (ev == 0 ? OFF_X : OFF_Y + (ev & 1) * HALF), src + (ev >> 1) * (34 * 14336) + (ev & 1) * 14336, HALF, bar);
                    if (ev >= 2) bulk_e(sb + OFF_X + X_STAT + (ev & 1) * 4096, ssrc + (ev & 1) * 512, 4096, bar);
                    if (ev) PROFH(4 + ev);
                    ev++; ok >>= 8;
                }
                if (n > SPIN_LIMIT) __trap();
            }
#pragma unroll 1
            for (int ps = 0; ps < 2; ps++) {
                mbar_wait(BAR(B_PUB + 6 + ps), 0);
                if (lane < 4) wait_flag(g_flag + (6 + ps) * 128 + 8 * r + 2 * lane + kh, target);
                warp_arrive(BAR(B_HRDY + ps));
                PROFH(10 + ps);
            }
        } else {
            if (lane == 0) {
#pragma unroll 1
                for (int k = 0; k < 8; k++) {
                    mbar_wait(BAR(B_PUB + k), 0);
                    fence_gpu();
                    st_relaxed(g_flag + k * 128 + b, target);
                    if (k >= 3 && k <= 5) PROFH1(k - 3);
                }
            }
        }
    }
}

typedef CUresult (*EncodeFn)(CUtensorMap*, CUtensorMapDataType, cuuint32_t, void*, const cuuint64_t*, const cuuint64_t*, const cuuint32_t*,
                             const cuuint32_t*, CUtensorMapInterleave, CUtensorMapSwizzle, CUtensorMapL2promotion, CUtensorMapFloatOOBfill);

static void make_map(EncodeFn fn, CUtensorMap* m, const void* ptr, uint64_t d0, uint64_t d1, uint64_t d2, uint64_t s1, uint64_t s2,
                     uint32_t b0, uint32_t b1, uint32_t b2, CUtensorMapSwizzle sw) {
    cuuint64_t dims[3] = {d0, d1, d2}, strides[2] = {s1, s2};
    cuuint32_t box[3] = {b0, b1, b2}, es[3] = {1, 1, 1};
    CUresult rc = fn(m, CU_TENSOR_MAP_DATA_TYPE_BFLOAT16, 3, (void*)ptr, dims, strides, box, es, CU_TENSOR_MAP_INTERLEAVE_NONE, sw,
                     CU_TENSOR_MAP_L2_PROMOTION_L2_128B, CU_TENSOR_MAP_FLOAT_OOB_FILL_NONE);
    (void)rc;
}

extern "C" void kernel_launch(void* const* d_in, const int* in_sizes, int n_in, void* d_out, int out_size) {
    (void)in_sizes; (void)n_in; (void)out_size;
    static EncodeFn fn = nullptr;
    if (!fn) {
        cudaDriverEntryPointQueryResult st;
        cudaGetDriverEntryPoint("cuTensorMapEncodeTiled", (void**)&fn, cudaEnableDefault, &st);
        cudaFuncSetAttribute(fused_block_kernel, cudaFuncAttributeMaxDynamicSharedMemorySize, SMEM_BYTES);
    }
    Params p;
    p.x = (const bf16*)d_in[0];
    const bf16* wqkv = (const bf16*)d_in[1];
    p.wqkv = wqkv;
    p.wop = (const bf16*)d_in[2];
    p.wg = (const bf16*)d_in[4];
    p.wu = (const bf16*)d_in[5];
    p.wd = (const bf16*)d_in[6];
    p.c = (const bf16*)d_in[7];
    p.wmod = (const bf16*)d_in[8];
    p.out = (bf16*)d_out;
    p.zero = 0;
    make_map(fn, &p.wm, p.wmod, 2688, 448, 1, 5376, 5376 * 448, 16, 224, 1, CU_TENSOR_MAP_SWIZZLE_NONE);
    make_map(fn, &p.xm, p.x, 448, 2048, 1, 896, 896 * 2048, 64, 128, 1, CU_TENSOR_MAP_SWIZZLE_128B);
    make_map(fn, &p.qkv, wqkv, 1344, 448, 1, 2688, 2688 * 448, 64, 224, 1, CU_TENSOR_MAP_SWIZZLE_128B);
    make_map(fn, &p.wo, p.wop, 448, 448, 1, 896, 896 * 448, 64, 224, 1, CU_TENSOR_MAP_SWIZZLE_128B);
    make_map(fn, &p.ga, p.wg, 64, 448, 28, 3584, 128, 64, 32, 2, CU_TENSOR_MAP_SWIZZLE_128B);
    make_map(fn, &p.ua, p.wu, 64, 448, 28, 3584, 128, 64, 32, 2, CU_TENSOR_MAP_SWIZZLE_128B);
    make_map(fn, &p.gb, p.wg, 32, 448, 56, 3584, 64, 32, 32, 3, CU_TENSOR_MAP_SWIZZLE_64B);
    make_map(fn, &p.ub, p.wu, 32, 448, 56, 3584, 64, 32, 32, 3, CU_TENSOR_MAP_SWIZZLE_64B);
    make_map(fn, &p.dn, p.wd, 448, 1792, 1, 896, 896 * 1792, 64, 32, 1, CU_TENSOR_MAP_SWIZZLE_128B);
    fused_block_kernel<<<GRID, 384, SMEM_BYTES>>>(p);
}
```

```cpp
#include <cuda_runtime.h>
#include <cuda_bf16.h>
#include <cuda.h>
#include <stdint.h>

typedef __nv_bfloat16 bf16;

template<int TB> __device__ __forceinline__ void wgmma_rs_56(float* d, uint32_t a0, uint32_t a1, uint32_t a2, uint32_t a3, uint64_t db, int sd) {
  asm volatile("{\n.reg .pred p;\nsetp.ne.b32 p, %33, 0;\n"
    "wgmma.mma_async.sync.aligned.m64n56k16.f32.bf16.bf16 {%0,%1,%2,%3,%4,%5,%6,%7,%8,%9,%10,%11,%12,%13,%14,%15,%16,%17,%18,%19,%20,%21,%22,%23,%24,%25,%26,%27}, {%28,%29,%30,%31}, %32, p, 1, 1, %34;\n}\n"
    : "+f"(d[0]),"+f"(d[1]),"+f"(d[2]),"+f"(d[3]),"+f"(d[4]),"+f"(d[5]),"+f"(d[6]),"+f"(d[7]),"+f"(d[8]),"+f"(d[9]),"+f"(d[10]),"+f"(d[11]),"+f"(d[12]),"+f"(d[13]),"+f"(d[14]),"+f"(d[15]),"+f"(d[16]),"+f"(d[17]),"+f"(d[18]),"+f"(d[19]),"+f"(d[20]),"+f"(d[21]),"+f"(d[22]),"+f"(d[23]),"+f"(d[24]),"+f"(d[25]),"+f"(d[26]),"+f"(d[27])
    : "r"(a0), "r"(a1), "r"(a2), "r"(a3), "l"(db), "r"(sd), "n"(TB));
}
template<int TB> __device__ __forceinline__ void wgmma_ss_56(float* d, uint64_t da, uint64_t db, int sd) {
  asm volatile("{\n.reg .pred p;\nsetp.ne.b32 p, %30, 0;\n"
    "wgmma.mma_async.sync.aligned.m64n56k16.f32.bf16.bf16 {%0,%1,%2,%3,%4,%5,%6,%7,%8,%9,%10,%11,%12,%13,%14,%15,%16,%17,%18,%19,%20,%21,%22,%23,%24,%25,%26,%27}, %28, %29, p, 1, 1, 0, %31;\n}\n"
    : "+f"(d[0]),"+f"(d[1]),"+f"(d[2]),"+f"(d[3]),"+f"(d[4]),"+f"(d[5]),"+f"(d[6]),"+f"(d[7]),"+f"(d[8]),"+f"(d[9]),"+f"(d[10]),"+f"(d[11]),"+f"(d[12]),"+f"(d[13]),"+f"(d[14]),"+f"(d[15]),"+f"(d[16]),"+f"(d[17]),"+f"(d[18]),"+f"(d[19]),"+f"(d[20]),"+f"(d[21]),"+f"(d[22]),"+f"(d[23]),"+f"(d[24]),"+f"(d[25]),"+f"(d[26]),"+f"(d[27])
    : "l"(da), "l"(db), "r"(sd), "n"(TB));
}
template<int TB> __device__ __forceinline__ void wgmma_rs_256(float* d, uint32_t a0, uint32_t a1, uint32_t a2, uint32_t a3, uint64_t db, int sd) {
  asm volatile("{\n.reg .pred p;\nsetp.ne.b32 p, %133, 0;\n"
    "wgmma.mma_async.sync.aligned.m64n256k16.f32.bf16.bf16 {%0,%1,%2,%3,%4,%5,%6,%7,%8,%9,%10,%11,%12,%13,%14,%15,%16,%17,%18,%19,%20,%21,%22,%23,%24,%25,%26,%27,%28,%29,%30,%31,%32,%33,%34,%35,%36,%37,%38,%39,%40,%41,%42,%43,%44,%45,%46,%47,%48,%49,%50,%51,%52,%53,%54,%55,%56,%57,%58,%59,%60,%61,%62,%63,%64,%65,%66,%67,%68,%69,%70,%71,%72,%73,%74,%75,%76,%77,%78,%79,%80,%81,%82,%83,%84,%85,%86,%87,%88,%89,%90,%91,%92,%93,%94,%95,%96,%97,%98,%99,%100,%101,%102,%103,%104,%105,%106,%107,%108,%109,%110,%111,%112,%113,%114,%115,%116,%117,%118,%119,%120,%121,%122,%123,%124,%125,%126,%127}, {%128,%129,%130,%131}, %132, p, 1, 1, %134;\n}\n"
    : "+f"(d[0]),"+f"(d[1]),"+f"(d[2]),"+f"(d[3]),"+f"(d[4]),"+f"(d[5]),"+f"(d[6]),"+f"(d[7]),"+f"(d[8]),"+f"(d[9]),"+f"(d[10]),"+f"(d[11]),"+f"(d[12]),"+f"(d[13]),"+f"(d[14]),"+f"(d[15]),"+f"(d[16]),"+f"(d[17]),"+f"(d[18]),"+f"(d[19]),"+f"(d[20]),"+f"(d[21]),"+f"(d[22]),"+f"(d[23]),"+f"(d[24]),"+f"(d[25]),"+f"(d[26]),"+f"(d[27]),"+f"(d[28]),"+f"(d[29]),"+f"(d[30]),"+f"(d[31]),"+f"(d[32]),"+f"(d[33]),"+f"(d[34]),"+f"(d[35]),"+f"(d[36]),"+f"(d[37]),"+f"(d[38]),"+f"(d[39]),"+f"(d[40]),"+f"(d[41]),"+f"(d[42]),"+f"(d[43]),"+f"(d[44]),"+f"(d[45]),"+f"(d[46]),"+f"(d[47]),"+f"(d[48]),"+f"(d[49]),"+f"(d[50]),"+f"(d[51]),"+f"(d[52]),"+f"(d[53]),"+f"(d[54]),"+f"(d[55]),"+f"(d[56]),"+f"(d[57]),"+f"(d[58]),"+f"(d[59]),"+f"(d[60]),"+f"(d[61]),"+f"(d[62]),"+f"(d[63]),"+f"(d[64]),"+f"(d[65]),"+f"(d[66]),"+f"(d[67]),"+f"(d[68]),"+f"(d[69]),"+f"(d[70]),"+f"(d[71]),"+f"(d[72]),"+f"(d[73]),"+f"(d[74]),"+f"(d[75]),"+f"(d[76]),"+f"(d[77]),"+f"(d[78]),"+f"(d[79]),"+f"(d[80]),"+f"(d[81]),"+f"(d[82]),"+f"(d[83]),"+f"(d[84]),"+f"(d[85]),"+f"(d[86]),"+f"(d[87]),"+f"(d[88]),"+f"(d[89]),"+f"(d[90]),"+f"(d[91]),"+f"(d[92]),"+f"(d[93]),"+f"(d[94]),"+f"(d[95]),"+f"(d[96]),"+f"(d[97]),"+f"(d[98]),"+f"(d[99]),"+f"(d[100]),"+f"(d[101]),"+f"(d[102]),"+f"(d[103]),"+f"(d[104]),"+f"(d[105]),"+f"(d[106]),"+f"(d[107]),"+f"(d[108]),"+f"(d[109]),"+f"(d[110]),"+f"(d[111]),"+f"(d[112]),"+f"(d[113]),"+f"(d[114]),"+f"(d[115]),"+f"(d[116]),"+f"(d[117]),"+f"(d[118]),"+f"(d[119]),"+f"(d[120]),"+f"(d[121]),"+f"(d[122]),"+f"(d[123]),"+f"(d[124]),"+f"(d[125]),"+f"(d[126]),"+f"(d[127])
    : "r"(a0), "r"(a1), "r"(a2), "r"(a3), "l"(db), "r"(sd), "n"(TB));
}
template<int TB> __device__ __forceinline__ void wgmma_ss_128(float* d, uint64_t da, uint64_t db, int sd) {
  asm volatile("{\n.reg .pred p;\nsetp.ne.b32 p, %66, 0;\n"
    "wgmma.mma_async.sync.aligned.m64n128k16.f32.bf16.bf16 {%0,%1,%2,%3,%4,%5,%6,%7,%8,%9,%10,%11,%12,%13,%14,%15,%16,%17,%18,%19,%20,%21,%22,%23,%24,%25,%26,%27,%28,%29,%30,%31,%32,%33,%34,%35,%36,%37,%38,%39,%40,%41,%42,%43,%44,%45,%46,%47,%48,%49,%50,%51,%52,%53,%54,%55,%56,%57,%58,%59,%60,%61,%62,%63}, %64, %65, p, 1, 1, 0, %67;\n}\n"
    : "+f"(d[0]),"+f"(d[1]),"+f"(d[2]),"+f"(d[3]),"+f"(d[4]),"+f"(d[5]),"+f"(d[6]),"+f"(d[7]),"+f"(d[8]),"+f"(d[9]),"+f"(d[10]),"+f"(d[11]),"+f"(d[12]),"+f"(d[13]),"+f"(d[14]),"+f"(d[15]),"+f"(d[16]),"+f"(d[17]),"+f"(d[18]),"+f"(d[19]),"+f"(d[20]),"+f"(d[21]),"+f"(d[22]),"+f"(d[23]),"+f"(d[24]),"+f"(d[25]),"+f"(d[26]),"+f"(d[27]),"+f"(d[28]),"+f"(d[29]),"+f"(d[30]),"+f"(d[31]),"+f"(d[32]),"+f"(d[33]),"+f"(d[34]),"+f"(d[35]),"+f"(d[36]),"+f"(d[37]),"+f"(d[38]),"+f"(d[39]),"+f"(d[40]),"+f"(d[41]),"+f"(d[42]),"+f"(d[43]),"+f"(d[44]),"+f"(d[45]),"+f"(d[46]),"+f"(d[47]),"+f"(d[48]),"+f"(d[49]),"+f"(d[50]),"+f"(d[51]),"+f"(d[52]),"+f"(d[53]),"+f"(d[54]),"+f"(d[55]),"+f"(d[56]),"+f"(d[57]),"+f"(d[58]),"+f"(d[59]),"+f"(d[60]),"+f"(d[61]),"+f"(d[62]),"+f"(d[63])
    : "l"(da), "l"(db), "r"(sd), "n"(TB));
}
template<int TB> __device__ __forceinline__ void wgmma_ss_64(float* d, uint64_t da, uint64_t db, int sd) {
  asm volatile("{\n.reg .pred p;\nsetp.ne.b32 p, %34, 0;\n"
    "wgmma.mma_async.sync.aligned.m64n64k16.f32.bf16.bf16 {%0,%1,%2,%3,%4,%5,%6,%7,%8,%9,%10,%11,%12,%13,%14,%15,%16,%17,%18,%19,%20,%21,%22,%23,%24,%25,%26,%27,%28,%29,%30,%31}, %32, %33, p, 1, 1, 0, %35;\n}\n"
    : "+f"(d[0]),"+f"(d[1]),"+f"(d[2]),"+f"(d[3]),"+f"(d[4]),"+f"(d[5]),"+f"(d[6]),"+f"(d[7]),"+f"(d[8]),"+f"(d[9]),"+f"(d[10]),"+f"(d[11]),"+f"(d[12]),"+f"(d[13]),"+f"(d[14]),"+f"(d[15]),"+f"(d[16]),"+f"(d[17]),"+f"(d[18]),"+f"(d[19]),"+f"(d[20]),"+f"(d[21]),"+f"(d[22]),"+f"(d[23]),"+f"(d[24]),"+f"(d[25]),"+f"(d[26]),"+f"(d[27]),"+f"(d[28]),"+f"(d[29]),"+f"(d[30]),"+f"(d[31])
    : "l"(da), "l"(db), "r"(sd), "n"(TB));
}
template<int TB> __device__ __forceinline__ void wgmma_ss_112(float* d, uint64_t da, uint64_t db, int sd) {
  asm volatile("{\n.reg .pred p;\nsetp.ne.b32 p, %58, 0;\n"
    "wgmma.mma_async.sync.aligned.m64n112k16.f32.bf16.bf16 {%0,%1,%2,%3,%4,%5,%6,%7,%8,%9,%10,%11,%12,%13,%14,%15,%16,%17,%18,%19,%20,%21,%22,%23,%24,%25,%26,%27,%28,%29,%30,%31,%32,%33,%34,%35,%36,%37,%38,%39,%40,%41,%42,%43,%44,%45,%46,%47,%48,%49,%50,%51,%52,%53,%54,%55}, %56, %57, p, 1, 1, 0, %59;\n}\n"
    : "+f"(d[0]),"+f"(d[1]),"+f"(d[2]),"+f"(d[3]),"+f"(d[4]),"+f"(d[5]),"+f"(d[6]),"+f"(d[7]),"+f"(d[8]),"+f"(d[9]),"+f"(d[10]),"+f"(d[11]),"+f"(d[12]),"+f"(d[13]),"+f"(d[14]),"+f"(d[15]),"+f"(d[16]),"+f"(d[17]),"+f"(d[18]),"+f"(d[19]),"+f"(d[20]),"+f"(d[21]),"+f"(d[22]),"+f"(d[23]),"+f"(d[24]),"+f"(d[25]),"+f"(d[26]),"+f"(d[27]),"+f"(d[28]),"+f"(d[29]),"+f"(d[30]),"+f"(d[31]),"+f"(d[32]),"+f"(d[33]),"+f"(d[34]),"+f"(d[35]),"+f"(d[36]),"+f"(d[37]),"+f"(d[38]),"+f"(d[39]),"+f"(d[40]),"+f"(d[41]),"+f"(d[42]),"+f"(d[43]),"+f"(d[44]),"+f"(d[45]),"+f"(d[46]),"+f"(d[47]),"+f"(d[48]),"+f"(d[49]),"+f"(d[50]),"+f"(d[51]),"+f"(d[52]),"+f"(d[53]),"+f"(d[54]),"+f"(d[55])
    : "l"(da), "l"(db), "r"(sd), "n"(TB));
}
template<int TB> __device__ __forceinline__ void wgmma_rs_112(float* d, uint32_t a0, uint32_t a1, uint32_t a2, uint32_t a3, uint64_t db, int sd) {
  asm volatile("{\n.reg .pred p;\nsetp.ne.b32 p, %61, 0;\n"
    "wgmma.mma_async.sync.aligned.m64n112k16.f32.bf16.bf16 {%0,%1,%2,%3,%4,%5,%6,%7,%8,%9,%10,%11,%12,%13,%14,%15,%16,%17,%18,%19,%20,%21,%22,%23,%24,%25,%26,%27,%28,%29,%30,%31,%32,%33,%34,%35,%36,%37,%38,%39,%40,%41,%42,%43,%44,%45,%46,%47,%48,%49,%50,%51,%52,%53,%54,%55}, {%56,%57,%58,%59}, %60, p, 1, 1, %62;\n}\n"
    : "+f"(d[0]),"+f"(d[1]),"+f"(d[2]),"+f"(d[3]),"+f"(d[4]),"+f"(d[5]),"+f"(d[6]),"+f"(d[7]),"+f"(d[8]),"+f"(d[9]),"+f"(d[10]),"+f"(d[11]),"+f"(d[12]),"+f"(d[13]),"+f"(d[14]),"+f"(d[15]),"+f"(d[16]),"+f"(d[17]),"+f"(d[18]),"+f"(d[19]),"+f"(d[20]),"+f"(d[21]),"+f"(d[22]),"+f"(d[23]),"+f"(d[24]),"+f"(d[25]),"+f"(d[26]),"+f"(d[27]),"+f"(d[28]),"+f"(d[29]),"+f"(d[30]),"+f"(d[31]),"+f"(d[32]),"+f"(d[33]),"+f"(d[34]),"+f"(d[35]),"+f"(d[36]),"+f"(d[37]),"+f"(d[38]),"+f"(d[39]),"+f"(d[40]),"+f"(d[41]),"+f"(d[42]),"+f"(d[43]),"+f"(d[44]),"+f"(d[45]),"+f"(d[46]),"+f"(d[47]),"+f"(d[48]),"+f"(d[49]),"+f"(d[50]),"+f"(d[51]),"+f"(d[52]),"+f"(d[53]),"+f"(d[54]),"+f"(d[55])
    : "r"(a0), "r"(a1), "r"(a2), "r"(a3), "l"(db), "r"(sd), "n"(TB));
}

constexpr int DM = 448;
constexpr int NCTA = 128;
#define MAPPING 1
#define GRID 132
#define PINGPONG 0
#define WIN 4
#define WIN_END 25
#define MAP_S 4
constexpr int SPIN_LIMIT = 1 << 22;

constexpr uint32_t OFF_X = 0, OFF_Y = 114688, OFF_MISC = 229376, SMEM_BYTES = 232448;
constexpr uint32_t Y_VR = 0, Y_K = 28672, Y_KOWN = 57344, Y_VOWN = 71680, Y_Q = 86016;
constexpr uint32_t HALF = 57344;
constexpr uint32_t M_BAR = OFF_MISC;
constexpr uint32_t M_ST = OFF_MISC + 512;
constexpr uint32_t M_G = OFF_MISC + 2304;
constexpr uint32_t M_EPOCH = OFF_MISC + 3040;
enum { B_XFULL = 0, B_FULLK = 7, B_FULLV = 8, B_FULLQ, B_KRFULL, B_VRFULL, B_WOFULL, B_XCH, B_FULL = 16, B_MOD1 = 28, B_MOD2, B_WMFULL,
       B_EMPTY = 32, B_XFREE = B_EMPTY + 12, B_GEMV, B_PEER,
       B_PUB = 47,
       B_WMFREE = 56, B_HRDY, B_GFULL = B_HRDY + 3, B_DONE = 31 };
constexpr uint32_t X_STAT = 49152;

__device__ uint32_t g_ticket;
__device__ __align__(128) uint32_t g_mod[8 * 6 * DM];
__device__ __align__(128) uint32_t g_flag[9 * 16 * 8];
__device__ __align__(128) uint32_t g_kv[17 * 8 * 2 * 3584];
__device__ __align__(128) uint32_t g_ox[2 * 34 * 14336];
#define g_o g_ox
#define g_x1 (g_ox + 34 * 14336)
__device__ __align__(128) float2 g_st[34 * 8 * 64];
__device__ __align__(128) uint32_t g_h2[17 * 224 * 512];
#define PROFH(id)
#define PROFH1(id)
#define PROFC(id)

struct alignas(64) Params {
    CUtensorMap wm, xm, qkv, wo, ga, ua, gb, ub, gc, uc, dn;
    const bf16 *x, *c, *wqkv, *wmod, *wg, *wu, *wd, *wop;
    bf16* out;
    uint32_t zero;
};

__device__ __forceinline__ void mbar_init(uint32_t bar, int cnt) { asm volatile("mbarrier.init.shared::cta.b64 [%0], %1;" ::"r"(bar), "r"(cnt) : "memory"); }
__device__ __forceinline__ void mbar_expect_tx(uint32_t bar, uint32_t bytes) { asm volatile("mbarrier.arrive.expect_tx.shared::cta.b64 _, [%0], %1;" ::"r"(bar), "r"(bytes) : "memory"); }
__device__ __forceinline__ void mbar_arrive(uint32_t bar) { asm volatile("mbarrier.arrive.shared::cta.b64 _, [%0];" ::"r"(bar) : "memory"); }
__device__ __forceinline__ void mbar_wait(uint32_t bar, uint32_t parity) {
    uint32_t ok; int n = 0;
    do {
        asm volatile("{\n.reg .pred p;\nmbarrier.try_wait.parity.shared::cta.b64 p, [%1], %2;\nselp.u32 %0, 1, 0, p;\n}" : "=r"(ok) : "r"(bar), "r"(parity) : "memory");
        if (++n > SPIN_LIMIT) __trap();
    } while (!ok);
}
__device__ __forceinline__ void mbar_wait_cluster(uint32_t bar, uint32_t parity) {
    uint32_t ok; int n = 0;
    do {
        asm volatile("{\n.reg .pred p;\nmbarrier.try_wait.parity.acquire.cluster.shared::cta.b64 p, [%1], %2;\nselp.u32 %0, 1, 0, p;\n}" : "=r"(ok) : "r"(bar), "r"(parity) : "memory");
        if (++n > SPIN_LIMIT) __trap();
    } while (!ok);
}
__device__ __forceinline__ void warp_arrive(uint32_t bar) {
    __syncwarp();
    asm volatile("{\n.reg .pred p;\nelect.sync _|p, 0xffffffff;\n@p mbarrier.arrive.shared::cta.b64 _, [%0];\n}" ::"r"(bar) : "memory");
}
__device__ __forceinline__ int opaque(int v) { return __shfl_sync(~0u, v, 0); }
__device__ __forceinline__ int fresh_tid() { int v; asm volatile("mov.u32 %0, %%tid.x;" : "=r"(v)); return v; }
__device__ __forceinline__ void bar_sync(int id, int n) { asm volatile("bar.sync %0, %1;" ::"r"(id), "r"(n) : "memory"); }
__device__ __forceinline__ void bar_arrive(int id, int n) { asm volatile("bar.arrive %0, %1;" ::"r"(id), "r"(n) : "memory"); }
__device__ __forceinline__ void fence_async_smem() { asm volatile("fence.proxy.async.shared::cta;" ::: "memory"); }
__device__ __forceinline__ void fence_async_global() { asm volatile("fence.proxy.async.global;" ::: "memory"); }
__device__ __forceinline__ void fence_gpu() { asm volatile("fence.release.gpu;" ::: "memory"); }
__device__ __forceinline__ void tma3(uint32_t dst, const CUtensorMap* m, int c0, int c1, int c2, uint32_t bar) {
    asm volatile("cp.async.bulk.tensor.3d.shared::cluster.global.mbarrier::complete_tx::bytes [%0], [%1, {%3, %4, %5}], [%2];"
                 ::"r"(dst), "l"(m), "r"(bar), "r"(c0), "r"(c1), "r"(c2) : "memory");
}
__device__ __forceinline__ void bulk_load(uint32_t dst, const void* src, uint32_t bytes, uint32_t bar) {
    asm volatile("cp.async.bulk.shared::cluster.global.mbarrier::complete_tx::bytes [%0], [%1], %2, [%3];" ::"r"(dst), "l"(src), "r"(bytes), "r"(bar) : "memory");
}
__device__ __forceinline__ void expect_e(uint32_t bar, uint32_t bytes) {
    asm volatile("{\n.reg .pred p;\nelect.sync _|p, 0xffffffff;\n@p mbarrier.arrive.expect_tx.shared::cta.b64 _, [%0], %1;\n}" ::"r"(bar), "r"(bytes) : "memory");
}
__device__ __forceinline__ void tma3_e(uint32_t dst, const CUtensorMap* m, int c0, int c1, int c2, uint32_t bar) {
    asm volatile("{\n.reg .pred p;\nelect.sync _|p, 0xffffffff;\n@p cp.async.bulk.tensor.3d.shared::cluster.global.mbarrier::complete_tx::bytes [%0], [%1, {%3, %4, %5}], [%2];\n}"
                 ::"r"(dst), "l"(m), "r"(bar), "r"(c0), "r"(c1), "r"(c2) : "memory");
}
__device__ __forceinline__ void bulk_e(uint32_t dst, const void* src, uint32_t bytes, uint32_t bar) {
    asm volatile("{\n.reg .pred p;\nelect.sync _|p, 0xffffffff;\n@p cp.async.bulk.shared::cluster.global.mbarrier::complete_tx::bytes [%0], [%1], %2, [%3];\n}"
                 ::"r"(dst), "l"(src), "r"(bytes), "r"(bar) : "memory");
}
__device__ __forceinline__ void init_e(uint32_t bar, int cnt) {
    asm volatile("{\n.reg .pred p;\nelect.sync _|p, 0xffffffff;\n@p mbarrier.init.shared::cta.b64 [%0], %1;\n}" ::"r"(bar), "r"(cnt) : "memory");
}
__device__ __forceinline__ void l2_prefetch_e(const void* src, uint32_t bytes) {
    asm volatile("{\n.reg .pred p;\nelect.sync _|p, 0xffffffff;\n@p cp.async.bulk.prefetch.L2.global [%0], %1;\n}" ::"l"(src), "r"(bytes) : "memory");
}
__device__ __forceinline__ uint32_t ld_relaxed(const uint32_t* p) { uint32_t v; asm volatile("ld.relaxed.gpu.global.u32 %0, [%1];" : "=r"(v) : "l"(p) : "memory"); return v; }
__device__ __forceinline__ void st_relaxed(uint32_t* p, uint32_t v) { asm volatile("st.relaxed.gpu.global.u32 [%0], %1;" ::"l"(p), "r"(v) : "memory"); }
__device__ __forceinline__ uint4 ld_relaxed4(const uint4* p) { uint4 v; asm volatile("ld.relaxed.gpu.global.v4.u32 {%0,%1,%2,%3}, [%4];" : "=r"(v.x), "=r"(v.y), "=r"(v.z), "=r"(v.w) : "l"(p) : "memory"); return v; }
__device__ __forceinline__ void st_relaxed4(uint4* p, uint4 v) { asm volatile("st.relaxed.gpu.global.v4.u32 [%0], {%1,%2,%3,%4};" ::"l"(p), "r"(v.x), "r"(v.y), "r"(v.z), "r"(v.w) : "memory"); }
__device__ __forceinline__ uint4 ldg_nc4(const void* p) { uint4 v; asm volatile("ld.global.nc.L1::no_allocate.v4.u32 {%0,%1,%2,%3}, [%4];" : "=r"(v.x), "=r"(v.y), "=r"(v.z), "=r"(v.w) : "l"(p)); return v; }
__device__ __forceinline__ uint32_t ldg_nc(const void* p) { uint32_t v; asm volatile("ld.global.nc.u32 %0, [%1];" : "=r"(v) : "l"(p)); return v; }
__device__ __forceinline__ uint32_t ld_acquire(const uint32_t* p) { uint32_t v; asm volatile("ld.acquire.gpu.global.u32 %0, [%1];" : "=r"(v) : "l"(p) : "memory"); return v; }
__device__ __forceinline__ uint4 lds4(uint32_t a) { uint4 v; asm volatile("ld.shared.v4.u32 {%0,%1,%2,%3}, [%4];" : "=r"(v.x), "=r"(v.y), "=r"(v.z), "=r"(v.w) : "r"(a) : "memory"); return v; }
__device__ __forceinline__ float2 lds2f(uint32_t a) { float2 v; asm volatile("ld.shared.v2.f32 {%0,%1}, [%2];" : "=f"(v.x), "=f"(v.y) : "r"(a) : "memory"); return v; }
__device__ __forceinline__ uint32_t lds1(uint32_t a) { uint32_t v; asm volatile("ld.shared.u32 %0, [%1];" : "=r"(v) : "r"(a) : "memory"); return v; }
__device__ __forceinline__ void sts4(uint32_t a, uint4 v) { asm volatile("st.shared.v4.u32 [%0], {%1,%2,%3,%4};" ::"r"(a), "r"(v.x), "r"(v.y), "r"(v.z), "r"(v.w) : "memory"); }
__device__ __forceinline__ void sts2(uint32_t a, uint32_t x, uint32_t y) { asm volatile("st.shared.v2.u32 [%0], {%1,%2};" ::"r"(a), "r"(x), "r"(y) : "memory"); }
__device__ __forceinline__ void sts1(uint32_t a, uint32_t v) { asm volatile("st.shared.u32 [%0], %1;" ::"r"(a), "r"(v) : "memory"); }
__device__ __forceinline__ void stsm4(uint32_t a, uint32_t r0, uint32_t r1, uint32_t r2, uint32_t r3) {
    asm volatile("stmatrix.sync.aligned.m8n8.x4.shared.b16 [%0], {%1,%2,%3,%4};" ::"r"(a), "r"(r0), "r"(r1), "r"(r2), "r"(r3));
}
__device__ __forceinline__ uint32_t pack2(float lo, float hi) { uint32_t r; asm("cvt.rn.bf16x2.f32 %0, %1, %2;" : "=r"(r) : "f"(hi), "f"(lo)); return r; }
__device__ __forceinline__ uint32_t pack2_relu(float lo, float hi) { uint32_t r; asm("cvt.rn.relu.bf16x2.f32 %0, %1, %2;" : "=r"(r) : "f"(hi), "f"(lo)); return r; }
__device__ __forceinline__ uint32_t hfma2(uint32_t a, uint32_t b, uint32_t c) { uint32_t r; asm("fma.rn.bf16x2 %0, %1, %2, %3;" : "=r"(r) : "r"(a), "r"(b), "r"(c)); return r; }
__device__ __forceinline__ uint32_t hmul2(uint32_t a, uint32_t b) { uint32_t r; asm("mul.rn.bf16x2 %0, %1, %2;" : "=r"(r) : "r"(a), "r"(b)); return r; }
__device__ __forceinline__ float bf_lo(uint32_t v) { return __uint_as_float(v << 16); }
__device__ __forceinline__ float bf_hi(uint32_t v) { return __uint_as_float(v & 0xFFFF0000u); }
__device__ __forceinline__ float bf_round(float v) { return bf_lo(pack2(v, 0.f)); }
__device__ __forceinline__ float ex2(float x) { float r; asm("ex2.approx.ftz.f32 %0, %1;" : "=f"(r) : "f"(x)); return r; }
__device__ __forceinline__ void mma16816(float* d, uint32_t a0, uint32_t a1, uint32_t a2, uint32_t a3, uint32_t b0, uint32_t b1) {
    asm("mma.sync.aligned.m16n8k16.row.col.f32.bf16.bf16.f32 {%0,%1,%2,%3}, {%4,%5,%6,%7}, {%8,%9}, {%0,%1,%2,%3};"
        : "+f"(d[0]), "+f"(d[1]), "+f"(d[2]), "+f"(d[3]) : "r"(a0), "r"(a1), "r"(a2), "r"(a3), "r"(b0), "r"(b1));
}
__device__ __forceinline__ void mma16816_first(float* d, uint32_t a0, uint32_t a1, uint32_t a2, uint32_t a3, uint32_t b0, uint32_t b1) {
    asm volatile("mma.sync.aligned.m16n8k16.row.col.f32.bf16.bf16.f32 {%0,%1,%2,%3}, {%4,%5,%6,%7}, {%8,%9}, {%10,%10,%10,%10};"
        : "=f"(d[0]), "=f"(d[1]), "=f"(d[2]), "=f"(d[3]) : "r"(a0), "r"(a1), "r"(a2), "r"(a3), "r"(b0), "r"(b1), "f"(0.f));
}
__device__ __forceinline__ void mma16816_v(float* d, uint32_t a0, uint32_t a1, uint32_t a2, uint32_t a3, uint32_t b0, uint32_t b1) {
    asm volatile("mma.sync.aligned.m16n8k16.row.col.f32.bf16.bf16.f32 {%0,%1,%2,%3}, {%4,%5,%6,%7}, {%8,%9}, {%0,%1,%2,%3};"
        : "+f"(d[0]), "+f"(d[1]), "+f"(d[2]), "+f"(d[3]) : "r"(a0), "r"(a1), "r"(a2), "r"(a3), "r"(b0), "r"(b1));
}
__device__ __forceinline__ void mma1688(float* d, uint32_t a0, uint32_t a1, uint32_t b0) {
    asm("mma.sync.aligned.m16n8k8.row.col.f32.bf16.bf16.f32 {%0,%1,%2,%3}, {%4,%5}, {%6}, {%0,%1,%2,%3};"
        : "+f"(d[0]), "+f"(d[1]), "+f"(d[2]), "+f"(d[3]) : "r"(a0), "r"(a1), "r"(b0));
}
__device__ __forceinline__ void ldsm4(uint32_t a, uint32_t* r) {
    asm volatile("ldmatrix.sync.aligned.m8n8.x4.shared.b16 {%0,%1,%2,%3}, [%4];" : "=r"(r[0]), "=r"(r[1]), "=r"(r[2]), "=r"(r[3]) : "r"(a));
}
__device__ __forceinline__ void ldsm4t(uint32_t a, uint32_t* r) {
    asm volatile("ldmatrix.sync.aligned.m8n8.x4.trans.shared.b16 {%0,%1,%2,%3}, [%4];" : "=r"(r[0]), "=r"(r[1]), "=r"(r[2]), "=r"(r[3]) : "r"(a));
}
__device__ __forceinline__ float rcp(float x) { float r; asm("rcp.approx.ftz.f32 %0, %1;" : "=f"(r) : "f"(x)); return r; }
__device__ __forceinline__ uint2 ld_relaxed2(const void* p) { uint2 v; asm volatile("ld.relaxed.gpu.global.v2.u32 {%0,%1}, [%2];" : "=r"(v.x), "=r"(v.y) : "l"(p) : "memory"); return v; }
__device__ __forceinline__ void st_relaxed2(void* p, uint32_t x, uint32_t y) { asm volatile("st.relaxed.gpu.global.v2.u32 [%0], {%1,%2};" ::"l"(p), "r"(max(x, 1u)), "r"(max(y, 1u)) : "memory"); }
__device__ __forceinline__ constexpr uint64_t dconst(uint32_t lbo, uint32_t sbo, uint32_t swz) {
    return ((uint64_t)(lbo >> 4) << 16) | ((uint64_t)(sbo >> 4) << 32) | ((uint64_t)swz << 62);
}
__device__ __forceinline__ uint64_t mkdesc(uint32_t addr, uint64_t c) { return c | (uint64_t)((addr & 0x3FFFF) >> 4); }
#define WG_FENCE() asm volatile("wgmma.fence.sync.aligned;" ::: "memory")
#define WG_COMMIT() asm volatile("wgmma.commit_group.sync.aligned;" ::: "memory")
#define WG_WAIT(n) asm volatile("wgmma.wait_group.sync.aligned %0;" ::"n"(n) : "memory")
template <int N> __device__ __forceinline__ void reg_fence(float* d) {
#pragma unroll
    for (int i = 0; i < N; i++) asm volatile("" : "+f"(d[i])::"memory");
}
template <int N> __device__ __forceinline__ void reg_def(float* d) {
#pragma unroll
    for (int i = 0; i < N; i++) asm volatile("" : "=f"(d[i]));
}
template <int N> __device__ __forceinline__ void reg_def(uint32_t* d) {
#pragma unroll
    for (int i = 0; i < N; i++) asm volatile("" : "=r"(d[i]));
}
__device__ __forceinline__ bool is_unset(uint4 v) { return min(min(v.x, v.y), min(v.z, v.w)) == 0u; }
__device__ __forceinline__ uint4 nz4(uint32_t a, uint32_t b, uint32_t c, uint32_t d) { return make_uint4(max(a, 1u), max(b, 1u), max(c, 1u), max(d, 1u)); }
__device__ __forceinline__ void wait_flag(const uint32_t* p, uint32_t target) {
    int n = 0;
    while ((int)(ld_relaxed(p) - target) < 0) { if (++n > SPIN_LIMIT) __trap(); }
    asm volatile("fence.acquire.gpu;" ::: "memory");
}
__device__ __forceinline__ float silu_bf(uint32_t cbits) {
    const float c = __uint_as_float(cbits << 16);
    return bf_round(__fdividef(c, 1.f + fminf(ex2(-1.4426950408889634f * c), 1e30f)));
}
__device__ __forceinline__ void gemv_part(uint32_t wmbuf, int npanel, int wp, int lane) {
    const uint32_t wa = wmbuf + wp * 512 + (8 * (lane >> 4) + (lane & 7)) * 32 + ((lane >> 3) & 1) * 16;
    uint2 B[4];
#pragma unroll
    for (int i = 0; i < 4; i++) { const float2 v = lds2f(wmbuf + 28672 + (wp + 8 * i) * 32 + (lane & 3) * 8); B[i] = make_uint2(__float_as_uint(v.x), __float_as_uint(v.y)); }
#pragma unroll 1
    for (int pn = 0; pn < npanel; pn++) {
        float d[4] = {};
        uint32_t A[16];
#pragma unroll
        for (int i = 0; i < 4; i++) ldsm4t(wa + pn * 14336 + (i < 3 || wp < 4 ? i : 0) * 4096, A + 4 * i);
#pragma unroll
        for (int i = 0; i < 4; i++) mma16816(d, A[4 * i], A[4 * i + 1], A[4 * i + 2], A[4 * i + 3], B[i].x, B[i].y);
        if ((lane & 3) == 0) {
            sts1(wmbuf + 29696 + (wp * 32 + pn * 16 + (lane >> 2)) * 4, __float_as_uint(d[0]));
            sts1(wmbuf + 29696 + (wp * 32 + pn * 16 + 8 + (lane >> 2)) * 4, __float_as_uint(d[2]));
        }
    }
}
__device__ __forceinline__ int pass_f(int fs, int ps) { return 224 * fs + ((fs & 1) ? (ps == 0 ? 96 : ps == 1 ? 32 : 0) : (ps == 0 ? 0 : ps == 1 ? 128 : 192)); }
__device__ __forceinline__ uint32_t slot_off(int l) { return (l < 3 || l > 6 ? l : l == 6 ? 3 : l + 1) * 16384; }
__device__ __forceinline__ void ln_coeffs(float mean, float msq, uint32_t& r2, uint32_t& n2) {
    const float rs = bf_round(rsqrtf(fmaxf(msq - mean * mean, 0.f) + 1e-5f));
    r2 = pack2(rs, rs);
    n2 = pack2(-mean * rs, -mean * rs);
}

template <int sec> __device__ __forceinline__ void ring_loader(const Params& p, uint32_t sb_, int r_, int j_) {
    const uint32_t sb = opaque(sb_);
    const int r = opaque(r_), j = opaque(j_), nq = j >> 1, fs = 4 * (j & 1) + nq;
    const int fa = pass_f(fs, 0), fb = pass_f(fs, 1), fc = pass_f(fs, 2);
#define BAR(i) (sb + M_BAR + 8 * (i))
#define kh (j & 1)
            int sl = 0;
#pragma unroll 1
            for (int s = 0; s < 28; s++) {
                if (s >= 1 && s < 6) mbar_wait(BAR(B_FULL + s - 1), 0);
                const int ps = s < 14 ? 0 : s < 21 ? 1 : 2;
                const uint32_t half = ps < 2 ? 8192 : 4096;
                mbar_wait(BAR(B_EMPTY + sl), (s >= 7 && s < 14) || s >= 21);
                expect_e(BAR(B_FULL + sl), half);
                tma3_e(sb + slot_off(sl) + sec * half, &p.ga + 2 * ps + sec, 0, ps ? 64 * sl : 32 * s, ps == 0 ? fa >> 6 : ps == 1 ? fb >> 6 : fc >> 5, BAR(B_FULL + sl));
                sl = sl == 6 ? 0 : sl + 1;
            }
            if (!sec) PROFH(3);
#pragma unroll 1
            for (int e = 0; e < 4; e++) {
                const uint32_t dst = sb + slot_off(e) + sec * 8192, bar = BAR(B_FULL + e);
                const int f = (e < 2 ? fa + 64 * e : e == 2 ? fb : fc) + 32 * sec;
                mbar_wait(BAR(B_EMPTY + e), 0);
                expect_e(bar, e == 3 && sec ? 0 : 8192);
                if (!(e == 3 && sec)) { tma3_e(dst, &p.dn, 112 * nq + 48, f, 0, bar); tma3_e(dst + 4096, &p.dn, 112 * nq, f, 0, bar); }
            }
            sl = 4;
            int e = 4;
#pragma unroll 1
            for (int grp = 0; grp < 9; grp++) {
                const int ps = grp >= 6 ? 2 : grp >= 3 ? 1 : 0;
                int sidx = grp - 3 * ps;
                if (sec && sidx == 0) { mbar_wait(BAR(B_HRDY + ps), 0); fence_async_global(); }
                sidx += sidx >= nq;
                int f = pass_f(4 * kh + sidx, ps);
#pragma unroll 1
                for (int k = 4 >> ps; k > 0; k--, e++, f += 32) {
                    const uint32_t dst = sb + slot_off(sl), bar = BAR(B_FULL + sl);
                    mbar_wait(BAR(B_EMPTY + sl), e >= 12 && e < 24);
                    if (e < WIN_END) mbar_wait(BAR(B_FULL + (sl >= WIN ? sl - WIN : sl + 12 - WIN)), e - WIN >= 12);
                    expect_e(bar, 8192);
                    if (!sec) { tma3_e(dst, &p.dn, 112 * nq + 48, f, 0, bar); tma3_e(dst + 4096, &p.dn, 112 * nq, f, 0, bar); }
                    else bulk_e(dst + 8192, g_h2 + (size_t)r * (224 * 512) + f * 64, 8192, bar);
                    sl = sl == 11 ? 0 : sl + 1;
                }
            }
            if (!sec) PROFH(4);
}

__global__ void __cluster_dims__(2, 1, 1) __launch_bounds__(384, 1) fused_block_kernel(const __grid_constant__ Params p) {
    extern __shared__ __align__(1024) unsigned char smem[];
    const uint32_t sb = (uint32_t)__cvta_generic_to_shared(smem);
    const int tid = threadIdx.x, lane = tid & 31, warp = __shfl_sync(~0u, tid >> 5, 0);
    const int m = blockIdx.x >> 1;
    int r, nq;
    {
        int g, i;
        if (m < MAP_S) { g = m < 4 ? 15 : 16; i = m & 3; }
        else if (m < MAP_S + 32) { g = (m - MAP_S) & 7; i = (m - MAP_S) >> 3; }
        else if (m < MAP_S + 60) { i = (m - MAP_S - 32) / 7; g = 8 + (m - MAP_S - 32) - 7 * i; }
        else { g = 16; i = m & 3; }
        r = g; nq = i;
    }
    const int j = opaque(2 * nq + (blockIdx.x & 1)), b = 8 * r + j, fs = 4 * kh + nq;
    const uint32_t sc = r == 16;
    if (lane == 0 && warp < 9 && warp != 6 && warp != 7) {
        const int i0 = warp == 8 ? 0 : 8 + 8 * warp, cnt = warp == 0 || warp == 8 ? 1 : warp < 3 ? 2 : 8;
#pragma unroll
        for (int k = 0; k < 8; k++) if (i0 + k != B_WMFULL) mbar_init(BAR(i0 + k), cnt);
        asm volatile("fence.mbarrier_init.release.cluster;" ::: "memory");
        fence_async_smem();
    }

    if (warp < 8) {
        const int w = warp >> 2, wi = warp & 3;
#define COORDS const int t = fresh_tid() & 127, lane = t & 31, q = lane & 3, lr = lane >> 2, ra = 64 * w + 16 * wi + lr; \
        const uint32_t lx = (lane >> 4) ^ (lane & 7), mrow = (64 * w + 16 * wi + ((lane >> 3) & 1) * 8 + (lane & 7)) * 128; \
        (void)q; (void)lr; (void)ra; (void)lx; (void)mrow;
        const int sid = 2 * (j & 3) + w;
#define RUN(k) (!sc || sid == (k))
#define WAIT(i, par) mbar_wait(BAR(i), (par) | sc)
        constexpr uint64_t DB128 = dconst(4096, 1024, 1);
        bar_arrive(9, 384);
        bar_sync(0, 384);
        asm volatile("barrier.cluster.arrive.relaxed.aligned;" ::: "memory");
        asm volatile("setmaxnreg.inc.sync.aligned.u32 224;");
        PROFC(0);
        uint32_t xr[16];
        {
            COORDS
            uint32_t h[112];
            if (RUN(0)) {
                float ds[4] = {}, da[2][4] = {}, db[2][4] = {};
                const uint32_t ONE2 = 0x3F803F80u;
                if (kh == 0) { WAIT(B_WMFULL, 0); gemv_part(sb + OFF_Y + HALF, 1, warp, lane); warp_arrive(BAR(B_GEMV)); }
#pragma unroll
                for (int kb = 0; kb < 7; kb++) {
                    WAIT(B_XFULL + kb, 0);
#pragma unroll
                    for (int k4 = 0; k4 < 4; k4++) ldsm4(sb + OFF_X + mrow + kb * 16384 + (((2 * k4) ^ lx) << 4), h + 16 * kb + 4 * k4);
#pragma unroll
                    for (int k4 = 0; k4 < 4; k4++) {
                        const uint32_t* f = h + 16 * kb + 4 * k4;
                        mma16816(ds, f[0], f[1], f[2], f[3], ONE2, ONE2);
                        mma1688(da[0], f[0], f[1], f[0]); mma1688(db[0], f[0], f[1], f[1]);
                        mma1688(da[1], f[2], f[3], f[2]); mma1688(db[1], f[2], f[3], f[3]);
                    }
                }
#pragma unroll
                for (int i = 0; i < 4; i++) {
                    const int ch = 7 * j + 2 * i + (lane >> 4);
                    ldsm4(sb + OFF_X + mrow + (ch >> 3) * 16384 + (((ch ^ lane) & 7) << 4), xr + 4 * i);
                }
                warp_arrive(BAR(B_XFREE));
                float qa = (lr & 1) ? da[0][1] + da[1][1] : da[0][0] + da[1][0];
                float qb = (lr & 1) ? db[0][3] + db[1][3] : db[0][2] + db[1][2];
                const int src = (lane & ~3) | (lr >> 1);
                qa = __shfl_sync(~0u, qa, src);
                qb = __shfl_sync(~0u, qb, src);
                uint32_t ra2, na2, rb2, nb2;
                ln_coeffs(ds[0] * (1.f / DM), qa * (1.f / DM), ra2, na2);
                ln_coeffs(ds[2] * (1.f / DM), qb * (1.f / DM), rb2, nb2);
#pragma unroll
                for (int i = 0; i < 112; i += 2) { h[i] = hfma2(h[i], ra2, na2); h[i + 1] = hfma2(h[i + 1], rb2, nb2); }
                if (kh == 1) { WAIT(B_WMFULL, 0); gemv_part(sb + OFF_Y + HALF, 2, warp, lane); warp_arrive(BAR(B_GEMV)); }
            } else { reg_def<112>(h); reg_def<16>(xr); }
            PROFC(1);
            if (RUN(1)) {
                float ak[28], av[28], aq[28];
                uint32_t kp[14], vp[14];
                const uint64_t bk0 = mkdesc(sb + OFF_Y, DB128) + kh, bv0 = mkdesc(sb + OFF_Y + HALF, DB128) + kh, bq0 = mkdesc(sb + OFF_X, DB128) + kh;
                uint32_t* kvg = g_kv + (size_t)(b * 2) * 3584 + (8 * w + 2 * wi) * 224 + lane;
                WAIT(B_FULLK, 0);
                WAIT(B_MOD1, 0);
                PROFC(2);
                reg_def<28>(ak);
#pragma unroll
                for (int g4 = 0; g4 < 4; g4++) {
#pragma unroll
                    for (int ks = 7 * g4; ks < 7 * g4 + 7; ks++) {
                        const uint4 st = *(const uint4*)(smem + M_ST + ks * 64 + q * 16);
                        h[4 * ks] = hfma2(h[4 * ks], st.x, st.y); h[4 * ks + 1] = hfma2(h[4 * ks + 1], st.x, st.y);
                        h[4 * ks + 2] = hfma2(h[4 * ks + 2], st.z, st.w); h[4 * ks + 3] = hfma2(h[4 * ks + 3], st.z, st.w);
                    }
                    WG_FENCE();
#pragma unroll
                    for (int ks = 7 * g4; ks < 7 * g4 + 7; ks++) wgmma_rs_56<1>(ak, h[4 * ks], h[4 * ks + 1], h[4 * ks + 2], h[4 * ks + 3], bk0 + ks * 128, ks != 0);
                }
                WG_COMMIT();
                PROFC(3);
                WAIT(B_FULLV, 0);
                reg_def<28>(av);
                WG_FENCE();
#pragma unroll
                for (int ks = 0; ks < 8; ks++) wgmma_rs_56<1>(av, h[4 * ks], h[4 * ks + 1], h[4 * ks + 2], h[4 * ks + 3], bv0 + ks * 128, ks != 0);
                WG_COMMIT();
                WG_WAIT(1);
                reg_fence<28>(ak);
#pragma unroll
                for (int g = 0; g < 7; g++) {
                    kp[2 * g] = pack2(ak[4 * g], ak[4 * g + 1]); kp[2 * g + 1] = pack2(ak[4 * g + 2], ak[4 * g + 3]);
                    kvg[g * 32] = kp[2 * g]; kvg[224 + g * 32] = kp[2 * g + 1];
                }
                warp_arrive(BAR(B_PUB));
                PROFC(4);
                WG_FENCE();
#pragma unroll
                for (int ks = 8; ks < 28; ks++) wgmma_rs_56<1>(av, h[4 * ks], h[4 * ks + 1], h[4 * ks + 2], h[4 * ks + 3], bv0 + ks * 128, 1);
                WG_COMMIT();
                WAIT(B_FULLQ, 0);
                reg_def<28>(aq);
                WG_FENCE();
#pragma unroll
                for (int ks = 0; ks < 8; ks++) wgmma_rs_56<1>(aq, h[4 * ks], h[4 * ks + 1], h[4 * ks + 2], h[4 * ks + 3], bq0 + ks * 128, ks != 0);
                WG_COMMIT();
                WG_WAIT(1);
                reg_fence<28>(av);
#pragma unroll
                for (int g = 0; g < 7; g++) {
                    vp[2 * g] = pack2(av[4 * g], av[4 * g + 1]); vp[2 * g + 1] = pack2(av[4 * g + 2], av[4 * g + 3]);
                    kvg[3584 + g * 32] = vp[2 * g]; kvg[3584 + 224 + g * 32] = vp[2 * g + 1];
                }
                warp_arrive(BAR(B_PUB + 1));
                PROFC(5);
                WG_FENCE();
#pragma unroll
                for (int ks = 8; ks < 28; ks++) wgmma_rs_56<1>(aq, h[4 * ks], h[4 * ks + 1], h[4 * ks + 2], h[4 * ks + 3], bq0 + ks * 128, 1);
                WG_COMMIT();
                WAIT(B_PUB + 1, 0);
                const uint32_t ko = sb + OFF_Y + Y_KOWN + (8 * w + 2 * wi) * 896 + lane * 4;
                const uint32_t qo = sb + OFF_Y + Y_Q + (8 * w + 2 * wi) * 1024 + lane * 4;
#pragma unroll
                for (int g = 0; g < 7; g++) {
                    sts1(ko + g * 128, kp[2 * g]); sts1(ko + 896 + g * 128, kp[2 * g + 1]);
                    sts1(ko + (Y_VOWN - Y_KOWN) + g * 128, vp[2 * g]); sts1(ko + (Y_VOWN - Y_KOWN) + 896 + g * 128, vp[2 * g + 1]);
                }
                WG_WAIT(0);
                reg_fence<28>(aq);
                __syncwarp();
                if (lane < 3 && w == 1) mbar_arrive(BAR(B_EMPTY + lane));
#pragma unroll
                for (int g = 0; g < 7; g++) {
                    const uint32_t q0 = pack2(aq[4 * g], aq[4 * g + 1]), q1 = pack2(aq[4 * g + 2], aq[4 * g + 3]);
                    if (g == 3) {
                        sts1(qo + 3 * 128, q < 2 ? q0 : 0u); sts1(qo + 1024 + 3 * 128, q < 2 ? q1 : 0u);
                        sts1(qo + 4 * 128, q < 2 ? 0u : q0); sts1(qo + 1024 + 4 * 128, q < 2 ? 0u : q1);
                    } else {
                        const int ch = g < 3 ? g : g + 1;
                        sts1(qo + ch * 128, q0); sts1(qo + 1024 + ch * 128, q1);
                    }
                }
                if (!sc) bar_sync(3, 256);
            }
        }
        PROFC(6);
        WAIT(B_KRFULL, 0);
        PROFC(7);
        if (RUN(2)) {
#pragma unroll 1
            for (int hf = sc; hf < 2; hf++) {
                COORDS
                float s[136];
                float na = 0.f, nb = 0.f;
                const float CS = 0.18898223650461361f * 1.4426950408889634f;
                const int kg0 = 8 * hf + 2 * wi;
                const int pmin = 16 - 8 * r - 4 * hf - wi;
                const float NEG = __int_as_float(0xFF800000);
                {
                    uint32_t F[8];
                    const uint32_t qa = sb + OFF_Y + Y_Q + (kg0 + ((lane >> 3) & 1)) * 1024 + (4 * w + (lane >> 4)) * 128 + (lane & 7) * 16;
                    ldsm4(qa, F); ldsm4(qa + 256, F + 4);
                    uint32_t ka = sb + OFF_Y + Y_K + kg0 * 896 + (3 * w + (lane >> 3)) * 128 + (lane & 7) * 16;
#pragma unroll
                    for (int g = 0; g < 34; g++) {
                        uint32_t B[4];
                        if (g >= 12 && g % 4 == 0) ka += __float_as_uint(s[4 * (g - 12)]) & p.zero;
                        ldsm4(ka + g * 896, B);
                        mma16816_first(s + 4 * g, F[0], F[1], F[2], F[3], B[0], B[1]);
                        mma16816_v(s + 4 * g, F[4], F[5], F[6], F[7], B[2], B[3]);
                    }
                    const bool c0 = 2 * q > lr, c1 = 2 * q + 1 > lr;
                    if (!c0) { s[0] = NEG; s[6] = NEG; }
                    if (!c1) { s[1] = NEG; s[7] = NEG; }
                    s[2] = NEG; s[3] = NEG;
                    if (c0) { s[128] = NEG; s[134] = NEG; }
                    if (c1) { s[129] = NEG; s[135] = NEG; }
                    s[132] = NEG; s[133] = NEG;
                    float ma = NEG, mb = NEG;
#pragma unroll
                    for (int pp = 0; pp < 17; pp++) {
                        const float* e = s + 8 * pp;
                        const float bias = pp < pmin ? NEG : 0.f;
                        ma = fmaxf(ma, fmaxf(fmaxf(e[0], e[1]), fmaxf(e[4], e[5])) + bias);
                        mb = fmaxf(mb, fmaxf(fmaxf(e[2], e[3]), fmaxf(e[6], e[7])) + bias);
                    }
                    ma = fmaxf(ma, __shfl_xor_sync(~0u, ma, 1)); mb = fmaxf(mb, __shfl_xor_sync(~0u, mb, 1));
                    ma = fmaxf(ma, __shfl_xor_sync(~0u, ma, 2)); mb = fmaxf(mb, __shfl_xor_sync(~0u, mb, 2));
                    na = -ma * CS; nb = -mb * CS;
                }
                PROFC(8 + 3 * hf);
                {
                    if (hf == 0) mbar_wait(BAR(B_VRFULL), 0);
                    float o[16] = {}, rs[4] = {};
                    const uint32_t va = sb + OFF_Y + Y_VR + (kg0 + ((lane >> 3) & 1)) * 896 + (3 * w + (lane >> 4)) * 128 + (lane & 7) * 16;
#pragma unroll
                    for (int pp = 0; pp < 17; pp++) {
                        uint32_t B[8];
                        const uint32_t v = va + pp * 1792 + (pp == 16 || (pp >= 9 && kg0 + 2 * pp >= 32) ? Y_VOWN - 32 * 896 : 0);
                        ldsm4t(v, B); ldsm4t(v + 256, B + 4);
                        float e[8];
#pragma unroll
                        for (int i = 0; i < 8; i++) e[i] = ex2(fmaf(s[8 * pp + i], CS, ((i & 2) ? nb : na) + (pp < pmin ? NEG : 0.f)));
                        const uint32_t p0 = pack2(e[0], e[1]), p1 = pack2(e[2], e[3]), p2 = pack2(e[4], e[5]), p3 = pack2(e[6], e[7]);
                        mma16816(rs, p0, p1, p2, p3, 0x3F803F80u, 0x3F803F80u);
#pragma unroll
                        for (int g = 0; g < 4; g++) mma16816(o + 4 * g, p0, p1, p2, p3, B[2 * g], B[2 * g + 1]);
                    }
                    PROFC(9 + 3 * hf);
                    const float ia = rcp(rs[0]), ib = rcp(rs[2]);
                    uint32_t* og = g_o + (size_t)(2 * r + hf) * 14336 + (7 * j + 3 * w) * 256 + wi * 64 + lane;
#pragma unroll
                    for (int g = 0; g < 4; g++) {
                        if ((g == 3 - 3 * w) ? ((q >> 1) == w) : true) {
                            og[g * 256] = pack2(o[4 * g] * ia, o[4 * g + 1] * ia);
                            og[g * 256 + 32] = pack2(o[4 * g + 2] * ib, o[4 * g + 3] * ib);
                        }
                    }
                    warp_arrive(BAR(B_PUB + 2 + hf));
                    PROFC(10 + 3 * hf);
                }
            }
        }
        uint32_t x1p[14];
        COORDS
        constexpr uint64_t DT = dconst(1024, 128, 0);
        if (RUN(4)) {
            float ac[28];
            const uint64_t ad = mkdesc(sb + (w ? OFF_Y + HALF : OFF_X), DT), bd = mkdesc(sb + OFF_X + HALF, DB128) + kh;
            WAIT(B_WOFULL, 0);
            WAIT(B_MOD2, 0);
            WAIT(B_GFULL + w, 0);
            PROFC(28);
            reg_def<28>(ac);
#pragma unroll 1
            for (int u = 0; u < 4; u++) {
                WG_FENCE();
#pragma unroll
                for (int i = 0; i < 7; i++) wgmma_ss_56<1>(ac, ad + (7 * u + i) * 128, bd + (7 * u + i) * 128, (u | i) != 0);
            }
            WG_COMMIT();
            WG_WAIT(0);
            reg_fence<28>(ac);
            PROFC(14);
            __syncwarp();
            if (lane < 3) mbar_arrive(BAR(B_EMPTY + 3 + lane));
            if (lane < 3 && w == 0) mbar_arrive(BAR(B_EMPTY + lane));
            float s1a = 0.f, s2a = 0.f, s1b = 0.f, s2b = 0.f;
            uint32_t* xo = g_x1 + (size_t)(2 * r + w) * 14336 + 7 * j * 256 + wi * 64 + lane;
#pragma unroll
            for (int g = 0; g < 7; g++) {
                const float2 ga = *(const float2*)(smem + M_G + (8 * g + 2 * q) * 4);
                x1p[2 * g] = pack2(fmaf(ga.x, ac[4 * g], bf_lo(xr[2 * g])), fmaf(ga.y, ac[4 * g + 1], bf_hi(xr[2 * g])));
                x1p[2 * g + 1] = pack2(fmaf(ga.x, ac[4 * g + 2], bf_lo(xr[2 * g + 1])), fmaf(ga.y, ac[4 * g + 3], bf_hi(xr[2 * g + 1])));
                xo[g * 256] = x1p[2 * g]; xo[g * 256 + 32] = x1p[2 * g + 1];
                const float u0 = bf_lo(x1p[2 * g]), u1 = bf_hi(x1p[2 * g]), u2 = bf_lo(x1p[2 * g + 1]), u3 = bf_hi(x1p[2 * g + 1]);
                s1a += u0 + u1; s2a += u0 * u0 + u1 * u1; s1b += u2 + u3; s2b += u2 * u2 + u3 * u3;
            }
            float ka = (q & 1) ? s2a : s1a, kb2 = (q & 1) ? s2b : s1b;
            ka += __shfl_xor_sync(~0u, (q & 1) ? s1a : s2a, 1); kb2 += __shfl_xor_sync(~0u, (q & 1) ? s1b : s2b, 1);
            const float kk = ((q & 2) ? kb2 : ka) + __shfl_xor_sync(~0u, (q & 2) ? ka : kb2, 2);
            ((float*)g_st)[(((2 * r + w) * 8 + j) * 64 + 16 * wi + lr + 4 * (q & 2)) * 2 + (q & 1)] = kk;
            __syncwarp();
            if (lane < 2) mbar_arrive(BAR(B_PUB + 4 + w));
        } else reg_def<14>(x1p);
        PROFC(15);
        uint32_t h2a[32], h2b[24];
        if (RUN(6)) {
            const int fa = pass_f(fs, 0), fb = pass_f(fs, 1), fc = pass_f(fs, 2);
            uint32_t* h2g = g_h2 + (size_t)r * (224 * 512) + (8 * w + 2 * wi) * 32 + lane;
            const uint64_t a0 = mkdesc(sb + OFF_Y + w * HALF, DT);
            const int s0 = sc ? 12 : 0;
            {
                WAIT(B_GFULL + 2 + w, 0);
                PROFC(16);
                float2 sa = make_float2(0.f, 0.f), sbb = sa;
#pragma unroll
                for (int jj = 0; jj < 8; jj++) {
                    const float2 u = lds2f(sb + OFF_X + X_STAT + w * 4096 + (jj * 64 + 16 * wi + lr) * 8), v = lds2f(sb + OFF_X + X_STAT + w * 4096 + (jj * 64 + 16 * wi + lr + 8) * 8);
                    sa.x += u.x; sa.y += u.y; sbb.x += v.x; sbb.y += v.y;
                }
                warp_arrive(BAR(B_EMPTY + 6));
                uint32_t ra2, na2, rb2, nb2;
                ln_coeffs(sa.x * (1.f / DM), sa.y * (1.f / DM), ra2, na2);
                ln_coeffs(sbb.x * (1.f / DM), sbb.y * (1.f / DM), rb2, nb2);
                const uint32_t ha = sb + OFF_Y + w * HALF + (lane >> 4) * 1024 + (2 * wi + ((lane >> 3) & 1)) * 128 + (lane & 7) * 16;
                const uint32_t sta = sb + M_ST + q * 16;
                auto prep = [&](int s, uint32_t* f) {
#pragma unroll
                    for (int i = 0; i < 2; i++) {
                        uint32_t x[4];
                        ldsm4(ha + (2 * s + i) * 2048, x);
                        const uint4 st = lds4(sta + (2 * s + i) * 64);
                        f[4 * i] = hfma2(hfma2(x[0], ra2, na2), st.x, st.y); f[4 * i + 1] = hfma2(hfma2(x[1], rb2, nb2), st.x, st.y);
                        f[4 * i + 2] = hfma2(hfma2(x[2], ra2, na2), st.z, st.w); f[4 * i + 3] = hfma2(hfma2(x[3], rb2, nb2), st.z, st.w);
                        stsm4(ha + (2 * s + i) * 2048, f[4 * i], f[4 * i + 1], f[4 * i + 2], f[4 * i + 3]);
                    }
                };
                float ac[128];
                uint32_t fr[3][8];
                reg_def<128>(ac);
                prep(s0, fr[0]);
                PROFC(17);
                int sl = 0, prev = 0;
#pragma unroll 1
                for (int s3 = s0; s3 < 14; s3 += 3) {
#pragma unroll
                    for (int e = 0; e < 3; e++) {
                        const int s = s3 + e;
                        if (s < 14) {
                            const uint32_t* f = fr[e];
                            WAIT(B_FULL + sl, s >= 7);
                            const uint64_t bd = mkdesc(sb + slot_off(sl), DB128);
                            WG_FENCE();
                            wgmma_rs_256<1>(ac, f[0], f[1], f[2], f[3], bd, s != 0);
                            wgmma_rs_256<1>(ac, f[4], f[5], f[6], f[7], bd + 128, 1);
                            WG_COMMIT();
                            if (s < 13) prep(s + 1, fr[(e + 1) % 3]);
                            WG_WAIT(1);
                            if (s > 0) warp_arrive(BAR(B_EMPTY + prev));
                            prev = sl; sl = sl == 6 ? 0 : sl + 1;
                        }
                    }
                }
                fence_async_smem();
                WG_WAIT(0);
                reg_fence<128>(ac);
                warp_arrive(BAR(B_EMPTY + 6));
                PROFC(18);
#pragma unroll
                for (int g = 0; g < 16; g++) {
                    h2a[2 * g] = hmul2(pack2_relu(ac[4 * g], ac[4 * g + 1]), pack2(ac[64 + 4 * g], ac[64 + 4 * g + 1]));
                    h2a[2 * g + 1] = hmul2(pack2_relu(ac[4 * g + 2], ac[4 * g + 3]), pack2(ac[64 + 4 * g + 2], ac[64 + 4 * g + 3]));
                    h2g[(fa / 8 + g) * 512] = h2a[2 * g]; h2g[(fa / 8 + g) * 512 + 32] = h2a[2 * g + 1];
                }
                warp_arrive(BAR(B_PUB + 6));
                bar_sync(1 + w, 128);
            }
            PROFC(19);
            {
                float ac[64];
                reg_def<64>(ac);
#pragma unroll 1
                for (int s = s0 >> 1; s < 7; s++) {
                    WAIT(B_FULL + s, 0);
                    const uint64_t ad = a0 + s * 512, bd = mkdesc(sb + slot_off(s), dconst(8192, 1024, 1));
                    WG_FENCE();
#pragma unroll
                    for (int k = 0; k < 4; k++) wgmma_ss_128<1>(ac, ad + k * 128, bd + k * 128, (s | k) != 0);
                    WG_COMMIT();
                    if (s > 0) { WG_WAIT(1); warp_arrive(BAR(B_EMPTY + s - 1)); }
                }
                WG_WAIT(0);
                reg_fence<64>(ac);
                warp_arrive(BAR(B_EMPTY + 6));
#pragma unroll
                for (int g = 0; g < 8; g++) {
                    h2b[2 * g] = hmul2(pack2_relu(ac[4 * g], ac[4 * g + 1]), pack2(ac[32 + 4 * g], ac[32 + 4 * g + 1]));
                    h2b[2 * g + 1] = hmul2(pack2_relu(ac[4 * g + 2], ac[4 * g + 3]), pack2(ac[32 + 4 * g + 2], ac[32 + 4 * g + 3]));
                    h2g[(fb / 8 + g) * 512] = h2b[2 * g]; h2g[(fb / 8 + g) * 512 + 32] = h2b[2 * g + 1];
                }
                warp_arrive(BAR(B_PUB + 7));
            }
            PROFC(27);
            {
                float ac[32];
                reg_def<32>(ac);
#pragma unroll 1
                for (int s = s0 >> 1; s < 7; s++) {
                    WAIT(B_FULL + s, 1);
                    const uint64_t ad = a0 + s * 512, bd = mkdesc(sb + slot_off(s), dconst(4096, 512, 2));
                    WG_FENCE();
#pragma unroll
                    for (int k = 0; k < 4; k++) wgmma_ss_64<1>(ac, ad + k * 128, bd + k * 64, (s | k) != 0);
                    WG_COMMIT();
                    if (s > 0) { WG_WAIT(1); warp_arrive(BAR(B_EMPTY + s - 1)); }
                }
                WG_WAIT(0);
                reg_fence<32>(ac);
                __syncwarp();
                if (lane < 6) mbar_arrive(BAR(B_EMPTY + 6 + lane));
                PROFC(20);
#pragma unroll
                for (int g = 0; g < 4; g++) {
                    h2b[16 + 2 * g] = hmul2(pack2_relu(ac[4 * g], ac[4 * g + 1]), pack2(ac[16 + 4 * g], ac[16 + 4 * g + 1]));
                    h2b[16 + 2 * g + 1] = hmul2(pack2_relu(ac[4 * g + 2], ac[4 * g + 3]), pack2(ac[16 + 4 * g + 2], ac[16 + 4 * g + 3]));
                    h2g[(fc / 8 + g) * 512] = h2b[16 + 2 * g]; h2g[(fc / 8 + g) * 512 + 32] = h2b[16 + 2 * g + 1];
                }
                warp_arrive(BAR(B_PUB + 8));
                asm volatile("barrier.cluster.wait.aligned;" ::: "memory");
                if (lane == 0 && !sc) {
                    uint32_t rb;
                    asm volatile("mapa.shared::cluster.u32 %0, %1, %2;" : "=r"(rb) : "r"(BAR(B_PEER)), "r"(kh ^ 1));
                    asm volatile("mbarrier.arrive.relaxed.cluster.shared::cluster.b64 _, [%0];" ::"r"(rb) : "memory");
                }
            }
        } else { reg_def<32>(h2a); reg_def<24>(h2b); }
        PROFC(21);
        if (RUN(7)) {
            float ac[56];
            reg_def<56>(ac);
            constexpr uint64_t DAN = dconst(2048, 128, 0);
#pragma unroll
            for (int e = 0; e < 4; e++) {
                WAIT(B_FULL + e, 0);
                const uint64_t bd = mkdesc(sb + slot_off(e), DB128);
                const uint32_t* hh = e < 2 ? h2a + 16 * e : h2b + 16 * (e - 2);
                WG_FENCE();
#pragma unroll
                for (int k = 0; k < (e < 3 ? 4 : 2); k++) wgmma_rs_112<1>(ac, hh[4 * k], hh[4 * k + 1], hh[4 * k + 2], hh[4 * k + 3], bd + (k >> 1) * 512 + (k & 1) * 128, (e | k) != 0);
                WG_COMMIT();
                if (e > 0) { WG_WAIT(1); warp_arrive(BAR(B_EMPTY + e - 1)); }
            }
            PROFC(22);
            int sl = 4, prev = 3;
#pragma unroll 1
            for (int e = 4; e < 25; e++) {
                WAIT(B_FULL + sl, e >= 12 && e < 24);
                if (e == 16) PROFC(23);
                const uint32_t sa = sb + slot_off(sl);
                const uint64_t ad = mkdesc(sa + 8192 + w * 1024, DAN), bd = mkdesc(sa, DB128);
                WG_FENCE();
                wgmma_ss_112<1>(ac, ad, bd, 1);
                wgmma_ss_112<1>(ac, ad + 256, bd + 128, 1);
                WG_COMMIT();
                if (e < 14) { WG_WAIT(1); warp_arrive(BAR(B_EMPTY + prev)); }
                prev = sl; sl = sl == 11 ? 0 : sl + 1;
            }
            mbar_wait_cluster(BAR(B_PEER), sc);
            WG_WAIT(0);
            reg_fence<56>(ac);
            PROFC(24);
            uint32_t rdst, rbar;
            asm volatile("mapa.shared::cluster.u32 %0, %1, %2;" : "=r"(rdst) : "r"(sb + OFF_Y + (5 + w) * 16384 + t * 16), "r"(kh ^ 1 ^ sc));
            asm volatile("mapa.shared::cluster.u32 %0, %1, %2;" : "=r"(rbar) : "r"(BAR(B_XCH + w)), "r"(kh ^ 1 ^ sc));
#define ACG(g, i) ac[4 * (((g) + 8) % 14) + (i)]
#pragma unroll
            for (int g = 0; g < 7; g++) {
                const float v0 = kh ? ACG(g, 0) : ACG(g + 7, 0), v1 = kh ? ACG(g, 1) : ACG(g + 7, 1);
                const float v2 = kh ? ACG(g, 2) : ACG(g + 7, 2), v3 = kh ? ACG(g, 3) : ACG(g + 7, 3);
                if (!sc) asm volatile("st.async.shared::cluster.mbarrier::complete_tx::bytes.v4.f32 [%0], {%1,%2,%3,%4}, [%5];"
                             ::"r"(rdst + g * 2048), "f"(v0), "f"(v1), "f"(v2), "f"(v3), "r"(rbar) : "memory");
            }
            mbar_wait_cluster(BAR(B_XCH + w), sc);
            PROFC(25);
            bf16* og = (sc ? (bf16*)(g_h2 + 16 * 224 * 512) : p.out + (size_t)128 * r * DM) + (size_t)ra * DM + 56 * j + 2 * q;
#pragma unroll
            for (int g = 0; g < 7; g++) {
                const uint4 rv = *(const uint4*)(smem + OFF_Y + (5 + w) * 16384 + t * 16 + g * 2048);
                const float2 gb = *(const float2*)(smem + M_G + 224 + (8 * g + 2 * q) * 4);
                const float v0 = (kh ? ACG(g + 7, 0) : ACG(g, 0)) + __uint_as_float(rv.x), v1 = (kh ? ACG(g + 7, 1) : ACG(g, 1)) + __uint_as_float(rv.y);
                const float v2 = (kh ? ACG(g + 7, 2) : ACG(g, 2)) + __uint_as_float(rv.z), v3 = (kh ? ACG(g + 7, 3) : ACG(g, 3)) + __uint_as_float(rv.w);
                *(uint32_t*)(og + 8 * g) = pack2(fmaf(gb.x, v0, bf_lo(x1p[2 * g])), fmaf(gb.y, v1, bf_hi(x1p[2 * g])));
                *(uint32_t*)(og + 8 * DM + 8 * g) = pack2(fmaf(gb.x, v2, bf_lo(x1p[2 * g + 1])), fmaf(gb.y, v3, bf_hi(x1p[2 * g + 1])));
            }
        }
        PROFC(26);
        bar_sync(1 + w, 128);
        if (wi == 0) warp_arrive(BAR(B_DONE));
    } else {
        const int lane = fresh_tid() & 31;
        const bool early = kh == 0, gemv = r < 14;
        const int mcol = early ? 16 * (4 * r + nq) : 2 * DM + 32 * (4 * r + nq);
        const uint32_t wmbuf = sb + OFF_Y + HALF;
        asm volatile("setmaxnreg.dec.sync.aligned.u32 56;");
        if (warp == 9) {
#pragma unroll
            for (int i = 56; i < 64; i++) init_e(BAR(i), 1);
            fence_async_smem();
        }
        if (warp == 8) { init_e(BAR(B_WMFULL), 2); fence_async_smem(); }
        bar_arrive(0, 384);
        asm volatile("barrier.cluster.arrive.relaxed.aligned;" ::: "memory");
        uint32_t target = 0;
        if (warp == 8) {
            if (!sc) {
                expect_e(BAR(B_WMFULL), gemv ? 28672 >> early : 0);
                if (early && gemv) { tma3_e(wmbuf, &p.wm, mcol, 0, 0, BAR(B_WMFULL)); tma3_e(wmbuf + 7168, &p.wm, mcol, 224, 0, BAR(B_WMFULL)); }
#pragma unroll 1
                for (int kb = 0; kb < 7; kb++) {
                    expect_e(BAR(B_XFULL + kb), 16384);
                    tma3_e(sb + OFF_X + kb * 16384, &p.xm, 64 * kb, 128 * r, 0, BAR(B_XFULL + kb));
                }
            }
#pragma unroll 1
            for (int mt = 0; mt < 4; mt++) {
                if (mt == 1) {
                    if (!early && gemv) {
#pragma unroll 1
                        for (int k = 0; k < 4; k++) tma3_e(wmbuf + k * 7168, &p.wm, mcol + (k >> 1) * 16, (k & 1) * 224, 0, BAR(B_WMFULL));
                    }
                    bar_sync(9, 384);
                    if (sc) return;
                    mbar_wait(BAR(B_MOD1), 0);
                    mbar_wait(BAR(B_WMFREE), 0);
                }
                if (mt == 2) mbar_wait(BAR(B_XFREE), 0);
                if (mt == 3) mbar_wait(BAR(B_VRFULL), 0);
                const uint32_t bar = BAR(mt == 3 ? B_WOFULL : B_FULLK + mt), dst = sb + (mt < 2 ? OFF_Y : OFF_X) + (mt & 1) * HALF;
                const int c0 = (mt < 2 ? DM + DM * mt : 0) + 56 * j - 8 * kh;
                if (!sc) {
                    expect_e(bar, HALF);
                    tma3_e(dst, mt == 3 ? &p.wo : &p.qkv, c0, 0, 0, bar);
                    tma3_e(dst + HALF / 2, mt == 3 ? &p.wo : &p.qkv, c0, 224, 0, bar);
                }
            }
            expect_e(BAR(B_XCH), 14336);
            expect_e(BAR(B_XCH + 1), 14336);
        } else {
            if (warp == 10 && !sc) {
                l2_prefetch_e((const char*)p.wqkv + (size_t)b * 9408, 9408);
                if (lane == 0) sts1(sb + M_EPOCH, atomicAdd(&g_ticket, 1u) / NCTA);
            }
            if (warp == 11) {
#pragma unroll
                for (int i = 0; i < 8; i++) {
                    const int wd = lane + 32 * i;
                    const uint32_t cb = i < 7 ? __ldg((const uint32_t*)p.c + wd) : 0u;
                    sts1(wmbuf + 28672 + (wd >> 3) * 32 + (wd & 3) * 8 + (wd & 4), pack2(silu_bf(cb & 0xFFFFu), silu_bf(cb >> 16)));
                }
            }
            bar_sync(9, 384);
            if (sc) return;
            target = lds1(sb + M_EPOCH) + 1;
            const uint32_t tag = target & 0xFFFFu;
            if (warp == 11) {
                warp_arrive(BAR(B_WMFULL));
                mbar_wait(BAR(B_GEMV), 0);
                float sum = 0.f;
#pragma unroll
                for (int i = 0; i < 8; i++) sum += *(const float*)(smem + OFF_Y + HALF + 29696 + (i * 32 + (early ? lane & 15 : lane)) * 4);
                const uint32_t word = (pack2(sum, 0.f) << 16) | tag;
                if (gemv) {
                    uint32_t* mg = g_mod + mcol + (early ? (lane & 15) + (lane >> 4) * 4 * 6 * DM : lane);
#pragma unroll
                    for (int i = 0; i < 8; i++) if (i < 4 || !early) st_relaxed(mg + i * 6 * DM, word);
                }
                warp_arrive(BAR(B_WMFREE));
            }
            const uint4* modp = (const uint4*)g_mod + (r & 7) * (6 * DM / 4);
            const bool p2 = warp == 11;
            mbar_wait(BAR(p2 ? B_PUB : B_XFULL + 4), 0);
#pragma unroll 1
            for (int it = p2 ? 0 : warp - 9; it < (p2 ? 2 : warp - 8); it++) {
                const int i0 = lane + 32 * it, imax = p2 ? 251 : 223;
                uint4 v[4];
#pragma unroll 1
                for (int n = 0;; n++) {
                    uint32_t bad = 0;
#pragma unroll
                    for (int k = 0; k < 4; k++) {
                        const int i = min(i0 + 64 * k, imax);
                        v[k] = ld_relaxed4(modp + (i < 224 ? (p2 ? 336 : 0) + i : (i < 238 ? 14 * j + i : 14 * j + i + 322)));
                        bad |= (v[k].x ^ tag) | (v[k].y ^ tag) | (v[k].z ^ tag) | (v[k].w ^ tag);
                    }
                    if (!__any_sync(~0u, bad & 0xFFFFu)) break;
                    if (n > SPIN_LIMIT) __trap();
                }
#pragma unroll
                for (int k = 0; k < 4; k++) {
                    const int i = min(i0 + 64 * k, imax);
                    if (i < 224) {
                        const int isc = i >= 112, c4 = i - 112 * isc;
                        const float one = isc ? 1.f : 0.f;
                        const uint32_t a = sb + M_ST + (c4 >> 2) * 64 + (c4 & 1) * 32 + (c4 & 2) * 4 + (isc ? 0 : 4);
                        sts1(a, pack2(bf_hi(v[k].x) + one, bf_hi(v[k].y) + one));
                        sts1(a + 16, pack2(bf_hi(v[k].z) + one, bf_hi(v[k].w) + one));
                    } else {
                        sts4(sb + M_G + (i - 224) * 16, make_uint4(v[k].x & 0xFFFF0000u, v[k].y & 0xFFFF0000u, v[k].z & 0xFFFF0000u, v[k].w & 0xFFFF0000u));
                    }
                }
                warp_arrive(BAR(p2 ? B_MOD2 : B_MOD1));
            }
            if (warp == 9) {
#pragma unroll 1
                for (int kv = 0; kv < 2; kv++) {
                    mbar_wait(BAR(B_PUB + kv), 0);
                    if (lane >= 1 && lane <= 2 && r >= lane) wait_flag(g_flag + kv * 128 + b - 8 * lane, target);
                    __syncwarp();
                    fence_async_global();
                    const uint32_t dst = sb + OFF_Y + (kv ? Y_VR : Y_K);
                    expect_e(BAR(B_KRFULL + kv), r >= 2 ? 28672 : r == 1 ? 14336 : 0);
                    if (r >= 2) bulk_e(dst, g_kv + (size_t)((b - 16) * 2 + kv) * 3584, 14336, BAR(B_KRFULL + kv));
                    if (r >= 1) bulk_e(dst + 14336, g_kv + (size_t)((b - 8) * 2 + kv) * 3584, 14336, BAR(B_KRFULL + kv));
                }
            } else if (warp == 11) {
                mbar_wait(BAR(B_VRFULL), 0);
                l2_prefetch_e((const char*)p.wg + (size_t)b * 12544, 12544);
                l2_prefetch_e((const char*)p.wu + (size_t)b * 12544, 12544);
                l2_prefetch_e((const char*)p.wd + (size_t)b * 12544, 12544);
            }
        }
        if (warp == 8 || warp == 11) {
            const int sec = warp == 11;
            if (sec) ring_loader<1>(p, sb, r, j); else ring_loader<0>(p, sb, r, j);
            mbar_wait(BAR(B_DONE), 0);
        } else if (warp == 9) {
#pragma unroll
            for (int ev = 0; ev < 4; ev++) expect_e(BAR(B_GFULL + ev), ev < 2 ? HALF : HALF + 4096);
            mbar_wait(BAR(B_PUB + 2), 0);
            const uint32_t* fp = g_flag + (2 + (lane >> 3)) * 128 + 8 * r + (lane & 7);
            const uint32_t* src = g_ox + (size_t)2 * r * 14336;
            const float2* ssrc = g_st + 2 * r * 512;
#pragma unroll 1
            for (int n = 0, ev = 0; ev < 4; n++) {
                if (ev == 1) mbar_wait(BAR(B_PUB + 3), 0);
                uint32_t ok = __ballot_sync(~0u, (int)(ld_relaxed(fp) - target) >= 0) >> (8 * ev);
                while ((ok & 0xFFu) == 0xFFu) {
                    asm volatile("fence.acquire.gpu;" ::: "memory");
                    fence_async_global();
                    const uint32_t bar = BAR(B_GFULL + ev);
                    bulk_e(sb + (ev == 0 ? OFF_X : OFF_Y + (ev & 1) * HALF), src + (ev >> 1) * (34 * 14336) + (ev & 1) * 14336, HALF, bar);
                    if (ev >= 2) bulk_e(sb + OFF_X + X_STAT + (ev & 1) * 4096, ssrc + (ev & 1) * 512, 4096, bar);
                    if (ev) PROFH(4 + ev);
                    ev++; ok >>= 8;
                }
                if (n > SPIN_LIMIT) __trap();
            }
#pragma unroll 1
            for (int ps = 0; ps < 3; ps++) {
                mbar_wait(BAR(B_PUB + 6 + ps), 0);
                if (lane < 4) wait_flag(g_flag + (6 + ps) * 128 + 8 * r + 2 * lane + kh, target);
                warp_arrive(BAR(B_HRDY + ps));
                PROFH(9 + ps);
            }
        } else {
            if (lane == 0) {
#pragma unroll 1
                for (int k = 0; k < 9; k++) {
                    mbar_wait(BAR(B_PUB + k), 0);
                    fence_gpu();
                    st_relaxed(g_flag + k * 128 + b, target);
                    if (k >= 3 && k <= 5) PROFH1(k - 3);
                }
            }
        }
    }
}

typedef CUresult (*EncodeFn)(CUtensorMap*, CUtensorMapDataType, cuuint32_t, void*, const cuuint64_t*, const cuuint64_t*, const cuuint32_t*,
                             const cuuint32_t*, CUtensorMapInterleave, CUtensorMapSwizzle, CUtensorMapL2promotion, CUtensorMapFloatOOBfill);

static void make_map(EncodeFn fn, CUtensorMap* m, const void* ptr, uint64_t d0, uint64_t d1, uint64_t d2, uint64_t s1, uint64_t s2,
                     uint32_t b0, uint32_t b1, uint32_t b2, CUtensorMapSwizzle sw) {
    cuuint64_t dims[3] = {d0, d1, d2}, strides[2] = {s1, s2};
    cuuint32_t box[3] = {b0, b1, b2}, es[3] = {1, 1, 1};
    CUresult rc = fn(m, CU_TENSOR_MAP_DATA_TYPE_BFLOAT16, 3, (void*)ptr, dims, strides, box, es, CU_TENSOR_MAP_INTERLEAVE_NONE, sw,
                     CU_TENSOR_MAP_L2_PROMOTION_L2_128B, CU_TENSOR_MAP_FLOAT_OOB_FILL_NONE);
    (void)rc;
}

extern "C" void kernel_launch(void* const* d_in, const int* in_sizes, int n_in, void* d_out, int out_size) {
    (void)in_sizes; (void)n_in; (void)out_size;
    static EncodeFn fn = nullptr;
    if (!fn) {
        cudaDriverEntryPointQueryResult st;
        cudaGetDriverEntryPoint("cuTensorMapEncodeTiled", (void**)&fn, cudaEnableDefault, &st);
        cudaFuncSetAttribute(fused_block_kernel, cudaFuncAttributeMaxDynamicSharedMemorySize, SMEM_BYTES);
    }
    Params p;
    p.x = (const bf16*)d_in[0];
    const bf16* wqkv = (const bf16*)d_in[1];
    p.wqkv = wqkv;
    p.wop = (const bf16*)d_in[2];
    p.wg = (const bf16*)d_in[4];
    p.wu = (const bf16*)d_in[5];
    p.wd = (const bf16*)d_in[6];
    p.c = (const bf16*)d_in[7];
    p.wmod = (const bf16*)d_in[8];
    p.out = (bf16*)d_out;
    p.zero = 0;
    make_map(fn, &p.wm, p.wmod, 2688, 448, 1, 5376, 5376 * 448, 16, 224, 1, CU_TENSOR_MAP_SWIZZLE_NONE);
    make_map(fn, &p.xm, p.x, 448, 2048, 1, 896, 896 * 2048, 64, 128, 1, CU_TENSOR_MAP_SWIZZLE_128B);
    make_map(fn, &p.qkv, wqkv, 1344, 448, 1, 2688, 2688 * 448, 64, 224, 1, CU_TENSOR_MAP_SWIZZLE_128B);
    make_map(fn, &p.wo, p.wop, 448, 448, 1, 896, 896 * 448, 64, 224, 1, CU_TENSOR_MAP_SWIZZLE_128B);
    make_map(fn, &p.ga, p.wg, 64, 448, 28, 3584, 128, 64, 32, 2, CU_TENSOR_MAP_SWIZZLE_128B);
    make_map(fn, &p.ua, p.wu, 64, 448, 28, 3584, 128, 64, 32, 2, CU_TENSOR_MAP_SWIZZLE_128B);
    make_map(fn, &p.gb, p.wg, 64, 448, 28, 3584, 128, 64, 64, 1, CU_TENSOR_MAP_SWIZZLE_128B);
    make_map(fn, &p.ub, p.wu, 64, 448, 28, 3584, 128, 64, 64, 1, CU_TENSOR_MAP_SWIZZLE_128B);
    make_map(fn, &p.gc, p.wg, 32, 448, 56, 3584, 64, 32, 64, 1, CU_TENSOR_MAP_SWIZZLE_64B);
    make_map(fn, &p.uc, p.wu, 32, 448, 56, 3584, 64, 32, 64, 1, CU_TENSOR_MAP_SWIZZLE_64B);
    make_map(fn, &p.dn, p.wd, 448, 1792, 1, 896, 896 * 1792, 64, 32, 1, CU_TENSOR_MAP_SWIZZLE_128B);
    fused_block_kernel<<<GRID, 384, SMEM_BYTES>>>(p);
}
```

```cpp
#include <cuda_runtime.h>
#include <cuda_bf16.h>
#include <cuda.h>
#include <stdint.h>

typedef __nv_bfloat16 bf16;

template<int TB> __device__ __forceinline__ void wgmma_rs_56(float* d, uint32_t a0, uint32_t a1, uint32_t a2, uint32_t a3, uint64_t db, int sd) {
  asm volatile("{\n.reg .pred p;\nsetp.ne.b32 p, %33, 0;\n"
    "wgmma.mma_async.sync.aligned.m64n56k16.f32.bf16.bf16 {%0,%1,%2,%3,%4,%5,%6,%7,%8,%9,%10,%11,%12,%13,%14,%15,%16,%17,%18,%19,%20,%21,%22,%23,%24,%25,%26,%27}, {%28,%29,%30,%31}, %32, p, 1, 1, %34;\n}\n"
    : "+f"(d[0]),"+f"(d[1]),"+f"(d[2]),"+f"(d[3]),"+f"(d[4]),"+f"(d[5]),"+f"(d[6]),"+f"(d[7]),"+f"(d[8]),"+f"(d[9]),"+f"(d[10]),"+f"(d[11]),"+f"(d[12]),"+f"(d[13]),"+f"(d[14]),"+f"(d[15]),"+f"(d[16]),"+f"(d[17]),"+f"(d[18]),"+f"(d[19]),"+f"(d[20]),"+f"(d[21]),"+f"(d[22]),"+f"(d[23]),"+f"(d[24]),"+f"(d[25]),"+f"(d[26]),"+f"(d[27])
    : "r"(a0), "r"(a1), "r"(a2), "r"(a3), "l"(db), "r"(sd), "n"(TB));
}
template<int TB> __device__ __forceinline__ void wgmma_ss_56(float* d, uint64_t da, uint64_t db, int sd) {
  asm volatile("{\n.reg .pred p;\nsetp.ne.b32 p, %30, 0;\n"
    "wgmma.mma_async.sync.aligned.m64n56k16.f32.bf16.bf16 {%0,%1,%2,%3,%4,%5,%6,%7,%8,%9,%10,%11,%12,%13,%14,%15,%16,%17,%18,%19,%20,%21,%22,%23,%24,%25,%26,%27}, %28, %29, p, 1, 1, 0, %31;\n}\n"
    : "+f"(d[0]),"+f"(d[1]),"+f"(d[2]),"+f"(d[3]),"+f"(d[4]),"+f"(d[5]),"+f"(d[6]),"+f"(d[7]),"+f"(d[8]),"+f"(d[9]),"+f"(d[10]),"+f"(d[11]),"+f"(d[12]),"+f"(d[13]),"+f"(d[14]),"+f"(d[15]),"+f"(d[16]),"+f"(d[17]),"+f"(d[18]),"+f"(d[19]),"+f"(d[20]),"+f"(d[21]),"+f"(d[22]),"+f"(d[23]),"+f"(d[24]),"+f"(d[25]),"+f"(d[26]),"+f"(d[27])
    : "l"(da), "l"(db), "r"(sd), "n"(TB));
}
template<int TB> __device__ __forceinline__ void wgmma_rs_256(float* d, uint32_t a0, uint32_t a1, uint32_t a2, uint32_t a3, uint64_t db, int sd) {
  asm volatile("{\n.reg .pred p;\nsetp.ne.b32 p, %133, 0;\n"
    "wgmma.mma_async.sync.aligned.m64n256k16.f32.bf16.bf16 {%0,%1,%2,%3,%4,%5,%6,%7,%8,%9,%10,%11,%12,%13,%14,%15,%16,%17,%18,%19,%20,%21,%22,%23,%24,%25,%26,%27,%28,%29,%30,%31,%32,%33,%34,%35,%36,%37,%38,%39,%40,%41,%42,%43,%44,%45,%46,%47,%48,%49,%50,%51,%52,%53,%54,%55,%56,%57,%58,%59,%60,%61,%62,%63,%64,%65,%66,%67,%68,%69,%70,%71,%72,%73,%74,%75,%76,%77,%78,%79,%80,%81,%82,%83,%84,%85,%86,%87,%88,%89,%90,%91,%92,%93,%94,%95,%96,%97,%98,%99,%100,%101,%102,%103,%104,%105,%106,%107,%108,%109,%110,%111,%112,%113,%114,%115,%116,%117,%118,%119,%120,%121,%122,%123,%124,%125,%126,%127}, {%128,%129,%130,%131}, %132, p, 1, 1, %134;\n}\n"
    : "+f"(d[0]),"+f"(d[1]),"+f"(d[2]),"+f"(d[3]),"+f"(d[4]),"+f"(d[5]),"+f"(d[6]),"+f"(d[7]),"+f"(d[8]),"+f"(d[9]),"+f"(d[10]),"+f"(d[11]),"+f"(d[12]),"+f"(d[13]),"+f"(d[14]),"+f"(d[15]),"+f"(d[16]),"+f"(d[17]),"+f"(d[18]),"+f"(d[19]),"+f"(d[20]),"+f"(d[21]),"+f"(d[22]),"+f"(d[23]),"+f"(d[24]),"+f"(d[25]),"+f"(d[26]),"+f"(d[27]),"+f"(d[28]),"+f"(d[29]),"+f"(d[30]),"+f"(d[31]),"+f"(d[32]),"+f"(d[33]),"+f"(d[34]),"+f"(d[35]),"+f"(d[36]),"+f"(d[37]),"+f"(d[38]),"+f"(d[39]),"+f"(d[40]),"+f"(d[41]),"+f"(d[42]),"+f"(d[43]),"+f"(d[44]),"+f"(d[45]),"+f"(d[46]),"+f"(d[47]),"+f"(d[48]),"+f"(d[49]),"+f"(d[50]),"+f"(d[51]),"+f"(d[52]),"+f"(d[53]),"+f"(d[54]),"+f"(d[55]),"+f"(d[56]),"+f"(d[57]),"+f"(d[58]),"+f"(d[59]),"+f"(d[60]),"+f"(d[61]),"+f"(d[62]),"+f"(d[63]),"+f"(d[64]),"+f"(d[65]),"+f"(d[66]),"+f"(d[67]),"+f"(d[68]),"+f"(d[69]),"+f"(d[70]),"+f"(d[71]),"+f"(d[72]),"+f"(d[73]),"+f"(d[74]),"+f"(d[75]),"+f"(d[76]),"+f"(d[77]),"+f"(d[78]),"+f"(d[79]),"+f"(d[80]),"+f"(d[81]),"+f"(d[82]),"+f"(d[83]),"+f"(d[84]),"+f"(d[85]),"+f"(d[86]),"+f"(d[87]),"+f"(d[88]),"+f"(d[89]),"+f"(d[90]),"+f"(d[91]),"+f"(d[92]),"+f"(d[93]),"+f"(d[94]),"+f"(d[95]),"+f"(d[96]),"+f"(d[97]),"+f"(d[98]),"+f"(d[99]),"+f"(d[100]),"+f"(d[101]),"+f"(d[102]),"+f"(d[103]),"+f"(d[104]),"+f"(d[105]),"+f"(d[106]),"+f"(d[107]),"+f"(d[108]),"+f"(d[109]),"+f"(d[110]),"+f"(d[111]),"+f"(d[112]),"+f"(d[113]),"+f"(d[114]),"+f"(d[115]),"+f"(d[116]),"+f"(d[117]),"+f"(d[118]),"+f"(d[119]),"+f"(d[120]),"+f"(d[121]),"+f"(d[122]),"+f"(d[123]),"+f"(d[124]),"+f"(d[125]),"+f"(d[126]),"+f"(d[127])
    : "r"(a0), "r"(a1), "r"(a2), "r"(a3), "l"(db), "r"(sd), "n"(TB));
}
template<int TB> __device__ __forceinline__ void wgmma_ss_128(float* d, uint64_t da, uint64_t db, int sd) {
  asm volatile("{\n.reg .pred p;\nsetp.ne.b32 p, %66, 0;\n"
    "wgmma.mma_async.sync.aligned.m64n128k16.f32.bf16.bf16 {%0,%1,%2,%3,%4,%5,%6,%7,%8,%9,%10,%11,%12,%13,%14,%15,%16,%17,%18,%19,%20,%21,%22,%23,%24,%25,%26,%27,%28,%29,%30,%31,%32,%33,%34,%35,%36,%37,%38,%39,%40,%41,%42,%43,%44,%45,%46,%47,%48,%49,%50,%51,%52,%53,%54,%55,%56,%57,%58,%59,%60,%61,%62,%63}, %64, %65, p, 1, 1, 0, %67;\n}\n"
    : "+f"(d[0]),"+f"(d[1]),"+f"(d[2]),"+f"(d[3]),"+f"(d[4]),"+f"(d[5]),"+f"(d[6]),"+f"(d[7]),"+f"(d[8]),"+f"(d[9]),"+f"(d[10]),"+f"(d[11]),"+f"(d[12]),"+f"(d[13]),"+f"(d[14]),"+f"(d[15]),"+f"(d[16]),"+f"(d[17]),"+f"(d[18]),"+f"(d[19]),"+f"(d[20]),"+f"(d[21]),"+f"(d[22]),"+f"(d[23]),"+f"(d[24]),"+f"(d[25]),"+f"(d[26]),"+f"(d[27]),"+f"(d[28]),"+f"(d[29]),"+f"(d[30]),"+f"(d[31]),"+f"(d[32]),"+f"(d[33]),"+f"(d[34]),"+f"(d[35]),"+f"(d[36]),"+f"(d[37]),"+f"(d[38]),"+f"(d[39]),"+f"(d[40]),"+f"(d[41]),"+f"(d[42]),"+f"(d[43]),"+f"(d[44]),"+f"(d[45]),"+f"(d[46]),"+f"(d[47]),"+f"(d[48]),"+f"(d[49]),"+f"(d[50]),"+f"(d[51]),"+f"(d[52]),"+f"(d[53]),"+f"(d[54]),"+f"(d[55]),"+f"(d[56]),"+f"(d[57]),"+f"(d[58]),"+f"(d[59]),"+f"(d[60]),"+f"(d[61]),"+f"(d[62]),"+f"(d[63])
    : "l"(da), "l"(db), "r"(sd), "n"(TB));
}
template<int TB> __device__ __forceinline__ void wgmma_ss_64(float* d, uint64_t da, uint64_t db, int sd) {
  asm volatile("{\n.reg .pred p;\nsetp.ne.b32 p, %34, 0;\n"
    "wgmma.mma_async.sync.aligned.m64n64k16.f32.bf16.bf16 {%0,%1,%2,%3,%4,%5,%6,%7,%8,%9,%10,%11,%12,%13,%14,%15,%16,%17,%18,%19,%20,%21,%22,%23,%24,%25,%26,%27,%28,%29,%30,%31}, %32, %33, p, 1, 1, 0, %35;\n}\n"
    : "+f"(d[0]),"+f"(d[1]),"+f"(d[2]),"+f"(d[3]),"+f"(d[4]),"+f"(d[5]),"+f"(d[6]),"+f"(d[7]),"+f"(d[8]),"+f"(d[9]),"+f"(d[10]),"+f"(d[11]),"+f"(d[12]),"+f"(d[13]),"+f"(d[14]),"+f"(d[15]),"+f"(d[16]),"+f"(d[17]),"+f"(d[18]),"+f"(d[19]),"+f"(d[20]),"+f"(d[21]),"+f"(d[22]),"+f"(d[23]),"+f"(d[24]),"+f"(d[25]),"+f"(d[26]),"+f"(d[27]),"+f"(d[28]),"+f"(d[29]),"+f"(d[30]),"+f"(d[31])
    : "l"(da), "l"(db), "r"(sd), "n"(TB));
}
template<int TB> __device__ __forceinline__ void wgmma_ss_112(float* d, uint64_t da, uint64_t db, int sd) {
  asm volatile("{\n.reg .pred p;\nsetp.ne.b32 p, %58, 0;\n"
    "wgmma.mma_async.sync.aligned.m64n112k16.f32.bf16.bf16 {%0,%1,%2,%3,%4,%5,%6,%7,%8,%9,%10,%11,%12,%13,%14,%15,%16,%17,%18,%19,%20,%21,%22,%23,%24,%25,%26,%27,%28,%29,%30,%31,%32,%33,%34,%35,%36,%37,%38,%39,%40,%41,%42,%43,%44,%45,%46,%47,%48,%49,%50,%51,%52,%53,%54,%55}, %56, %57, p, 1, 1, 0, %59;\n}\n"
    : "+f"(d[0]),"+f"(d[1]),"+f"(d[2]),"+f"(d[3]),"+f"(d[4]),"+f"(d[5]),"+f"(d[6]),"+f"(d[7]),"+f"(d[8]),"+f"(d[9]),"+f"(d[10]),"+f"(d[11]),"+f"(d[12]),"+f"(d[13]),"+f"(d[14]),"+f"(d[15]),"+f"(d[16]),"+f"(d[17]),"+f"(d[18]),"+f"(d[19]),"+f"(d[20]),"+f"(d[21]),"+f"(d[22]),"+f"(d[23]),"+f"(d[24]),"+f"(d[25]),"+f"(d[26]),"+f"(d[27]),"+f"(d[28]),"+f"(d[29]),"+f"(d[30]),"+f"(d[31]),"+f"(d[32]),"+f"(d[33]),"+f"(d[34]),"+f"(d[35]),"+f"(d[36]),"+f"(d[37]),"+f"(d[38]),"+f"(d[39]),"+f"(d[40]),"+f"(d[41]),"+f"(d[42]),"+f"(d[43]),"+f"(d[44]),"+f"(d[45]),"+f"(d[46]),"+f"(d[47]),"+f"(d[48]),"+f"(d[49]),"+f"(d[50]),"+f"(d[51]),"+f"(d[52]),"+f"(d[53]),"+f"(d[54]),"+f"(d[55])
    : "l"(da), "l"(db), "r"(sd), "n"(TB));
}
template<int TB> __device__ __forceinline__ void wgmma_rs_112(float* d, uint32_t a0, uint32_t a1, uint32_t a2, uint32_t a3, uint64_t db, int sd) {
  asm volatile("{\n.reg .pred p;\nsetp.ne.b32 p, %61, 0;\n"
    "wgmma.mma_async.sync.aligned.m64n112k16.f32.bf16.bf16 {%0,%1,%2,%3,%4,%5,%6,%7,%8,%9,%10,%11,%12,%13,%14,%15,%16,%17,%18,%19,%20,%21,%22,%23,%24,%25,%26,%27,%28,%29,%30,%31,%32,%33,%34,%35,%36,%37,%38,%39,%40,%41,%42,%43,%44,%45,%46,%47,%48,%49,%50,%51,%52,%53,%54,%55}, {%56,%57,%58,%59}, %60, p, 1, 1, %62;\n}\n"
    : "+f"(d[0]),"+f"(d[1]),"+f"(d[2]),"+f"(d[3]),"+f"(d[4]),"+f"(d[5]),"+f"(d[6]),"+f"(d[7]),"+f"(d[8]),"+f"(d[9]),"+f"(d[10]),"+f"(d[11]),"+f"(d[12]),"+f"(d[13]),"+f"(d[14]),"+f"(d[15]),"+f"(d[16]),"+f"(d[17]),"+f"(d[18]),"+f"(d[19]),"+f"(d[20]),"+f"(d[21]),"+f"(d[22]),"+f"(d[23]),"+f"(d[24]),"+f"(d[25]),"+f"(d[26]),"+f"(d[27]),"+f"(d[28]),"+f"(d[29]),"+f"(d[30]),"+f"(d[31]),"+f"(d[32]),"+f"(d[33]),"+f"(d[34]),"+f"(d[35]),"+f"(d[36]),"+f"(d[37]),"+f"(d[38]),"+f"(d[39]),"+f"(d[40]),"+f"(d[41]),"+f"(d[42]),"+f"(d[43]),"+f"(d[44]),"+f"(d[45]),"+f"(d[46]),"+f"(d[47]),"+f"(d[48]),"+f"(d[49]),"+f"(d[50]),"+f"(d[51]),"+f"(d[52]),"+f"(d[53]),"+f"(d[54]),"+f"(d[55])
    : "r"(a0), "r"(a1), "r"(a2), "r"(a3), "l"(db), "r"(sd), "n"(TB));
}

constexpr int DM = 448;
constexpr int NCTA = 128;
#define MAPPING 1
#define GRID 132
#define PINGPONG 0
#define WIN 4
#define WIN_END 25
#define MAP_S 4
constexpr int SPIN_LIMIT = 1 << 22;

constexpr uint32_t OFF_X = 0, OFF_Y = 114688, OFF_MISC = 229376, SMEM_BYTES = 232448;
constexpr uint32_t Y_VR = 0, Y_K = 28672, Y_KOWN = 57344, Y_VOWN = 71680, Y_Q = 86016;
constexpr uint32_t HALF = 57344;
constexpr uint32_t M_BAR = OFF_MISC;
constexpr uint32_t M_ST = OFF_MISC + 512;
constexpr uint32_t M_G = OFF_MISC + 2304;
constexpr uint32_t M_EPOCH = OFF_MISC + 3040;
enum { B_XFULL = 0, B_FULLK = 7, B_FULLV = 8, B_FULLQ, B_KRFULL, B_VRFULL, B_WOFULL, B_XCH, B_FULL = 16, B_MOD1 = 28, B_MOD2, B_WMFULL,
       B_EMPTY = 32, B_XFREE = B_EMPTY + 12, B_GEMV, B_PEER,
       B_PUB = 47,
       B_WMFREE = 56, B_HRDY, B_GFULL = B_HRDY + 3, B_DONE = 31 };
constexpr uint32_t X_STAT = 49152;

__device__ uint32_t g_ticket;
__device__ __align__(128) uint32_t g_mod[8 * 6 * DM];
__device__ __align__(128) uint32_t g_flag[9 * 16 * 8];
__device__ __align__(128) uint32_t g_kv[17 * 8 * 2 * 3584];
__device__ __align__(128) uint32_t g_ox[2 * 34 * 14336];
#define g_o g_ox
#define g_x1 (g_ox + 34 * 14336)
__device__ __align__(128) float2 g_st[34 * 8 * 64];
__device__ __align__(128) uint32_t g_h2[17 * 224 * 512];
#define PROFH(id)
#define PROFH1(id)
#define PROFC(id)

struct alignas(64) Params {
    CUtensorMap wm, xm, qkv, wo, ga, ua, gb, ub, gc, uc, dn;
    const bf16 *x, *c, *wqkv, *wmod, *wg, *wu, *wd, *wop;
    bf16* out;
    uint32_t zero;
};

__device__ __forceinline__ void mbar_init(uint32_t bar, int cnt) { asm volatile("mbarrier.init.shared::cta.b64 [%0], %1;" ::"r"(bar), "r"(cnt) : "memory"); }
__device__ __forceinline__ void mbar_expect_tx(uint32_t bar, uint32_t bytes) { asm volatile("mbarrier.arrive.expect_tx.shared::cta.b64 _, [%0], %1;" ::"r"(bar), "r"(bytes) : "memory"); }
__device__ __forceinline__ void mbar_arrive(uint32_t bar) { asm volatile("mbarrier.arrive.shared::cta.b64 _, [%0];" ::"r"(bar) : "memory"); }
__device__ __forceinline__ void mbar_wait(uint32_t bar, uint32_t parity) {
    uint32_t ok; int n = 0;
    do {
        asm volatile("{\n.reg .pred p;\nmbarrier.try_wait.parity.shared::cta.b64 p, [%1], %2;\nselp.u32 %0, 1, 0, p;\n}" : "=r"(ok) : "r"(bar), "r"(parity) : "memory");
        if (++n > SPIN_LIMIT) __trap();
    } while (!ok);
}
__device__ __forceinline__ void mbar_wait_cluster(uint32_t bar, uint32_t parity) {
    uint32_t ok; int n = 0;
    do {
        asm volatile("{\n.reg .pred p;\nmbarrier.try_wait.parity.acquire.cluster.shared::cta.b64 p, [%1], %2;\nselp.u32 %0, 1, 0, p;\n}" : "=r"(ok) : "r"(bar), "r"(parity) : "memory");
        if (++n > SPIN_LIMIT) __trap();
    } while (!ok);
}
__device__ __forceinline__ void warp_arrive(uint32_t bar) {
    __syncwarp();
    asm volatile("{\n.reg .pred p;\nelect.sync _|p, 0xffffffff;\n@p mbarrier.arrive.shared::cta.b64 _, [%0];\n}" ::"r"(bar) : "memory");
}
__device__ __forceinline__ int opaque(int v) { return __shfl_sync(~0u, v, 0); }
__device__ __forceinline__ int fresh_tid() { int v; asm volatile("mov.u32 %0, %%tid.x;" : "=r"(v)); return v; }
__device__ __forceinline__ void bar_sync(int id, int n) { asm volatile("bar.sync %0, %1;" ::"r"(id), "r"(n) : "memory"); }
__device__ __forceinline__ void bar_arrive(int id, int n) { asm volatile("bar.arrive %0, %1;" ::"r"(id), "r"(n) : "memory"); }
__device__ __forceinline__ void fence_async_smem() { asm volatile("fence.proxy.async.shared::cta;" ::: "memory"); }
__device__ __forceinline__ void fence_async_global() { asm volatile("fence.proxy.async.global;" ::: "memory"); }
__device__ __forceinline__ void fence_gpu() { asm volatile("fence.release.gpu;" ::: "memory"); }
__device__ __forceinline__ void tma3(uint32_t dst, const CUtensorMap* m, int c0, int c1, int c2, uint32_t bar) {
    asm volatile("cp.async.bulk.tensor.3d.shared::cluster.global.mbarrier::complete_tx::bytes [%0], [%1, {%3, %4, %5}], [%2];"
                 ::"r"(dst), "l"(m), "r"(bar), "r"(c0), "r"(c1), "r"(c2) : "memory");
}
__device__ __forceinline__ void bulk_load(uint32_t dst, const void* src, uint32_t bytes, uint32_t bar) {
    asm volatile("cp.async.bulk.shared::cluster.global.mbarrier::complete_tx::bytes [%0], [%1], %2, [%3];" ::"r"(dst), "l"(src), "r"(bytes), "r"(bar) : "memory");
}
__device__ __forceinline__ void expect_e(uint32_t bar, uint32_t bytes) {
    asm volatile("{\n.reg .pred p;\nelect.sync _|p, 0xffffffff;\n@p mbarrier.arrive.expect_tx.shared::cta.b64 _, [%0], %1;\n}" ::"r"(bar), "r"(bytes) : "memory");
}
__device__ __forceinline__ void tma3_e(uint32_t dst, const CUtensorMap* m, int c0, int c1, int c2, uint32_t bar) {
    asm volatile("{\n.reg .pred p;\nelect.sync _|p, 0xffffffff;\n@p cp.async.bulk.tensor.3d.shared::cluster.global.mbarrier::complete_tx::bytes [%0], [%1, {%3, %4, %5}], [%2];\n}"
                 ::"r"(dst), "l"(m), "r"(bar), "r"(c0), "r"(c1), "r"(c2) : "memory");
}
__device__ __forceinline__ void bulk_e(uint32_t dst, const void* src, uint32_t bytes, uint32_t bar) {
    asm volatile("{\n.reg .pred p;\nelect.sync _|p, 0xffffffff;\n@p cp.async.bulk.shared::cluster.global.mbarrier::complete_tx::bytes [%0], [%1], %2, [%3];\n}"
                 ::"r"(dst), "l"(src), "r"(bytes), "r"(bar) : "memory");
}
__device__ __forceinline__ void init_e(uint32_t bar, int cnt) {
    asm volatile("{\n.reg .pred p;\nelect.sync _|p, 0xffffffff;\n@p mbarrier.init.shared::cta.b64 [%0], %1;\n}" ::"r"(bar), "r"(cnt) : "memory");
}
__device__ __forceinline__ void l2_prefetch_e(const void* src, uint32_t bytes) {
    asm volatile("{\n.reg .pred p;\nelect.sync _|p, 0xffffffff;\n@p cp.async.bulk.prefetch.L2.global [%0], %1;\n}" ::"l"(src), "r"(bytes) : "memory");
}
__device__ __forceinline__ uint32_t ld_relaxed(const uint32_t* p) { uint32_t v; asm volatile("ld.relaxed.gpu.global.u32 %0, [%1];" : "=r"(v) : "l"(p) : "memory"); return v; }
__device__ __forceinline__ void st_relaxed(uint32_t* p, uint32_t v) { asm volatile("st.relaxed.gpu.global.u32 [%0], %1;" ::"l"(p), "r"(v) : "memory"); }
__device__ __forceinline__ uint4 ld_relaxed4(const uint4* p) { uint4 v; asm volatile("ld.relaxed.gpu.global.v4.u32 {%0,%1,%2,%3}, [%4];" : "=r"(v.x), "=r"(v.y), "=r"(v.z), "=r"(v.w) : "l"(p) : "memory"); return v; }
__device__ __forceinline__ void st_relaxed4(uint4* p, uint4 v) { asm volatile("st.relaxed.gpu.global.v4.u32 [%0], {%1,%2,%3,%4};" ::"l"(p), "r"(v.x), "r"(v.y), "r"(v.z), "r"(v.w) : "memory"); }
__device__ __forceinline__ uint4 ldg_nc4(const void* p) { uint4 v; asm volatile("ld.global.nc.L1::no_allocate.v4.u32 {%0,%1,%2,%3}, [%4];" : "=r"(v.x), "=r"(v.y), "=r"(v.z), "=r"(v.w) : "l"(p)); return v; }
__device__ __forceinline__ uint32_t ldg_nc(const void* p) { uint32_t v; asm volatile("ld.global.nc.u32 %0, [%1];" : "=r"(v) : "l"(p)); return v; }
__device__ __forceinline__ uint32_t ld_acquire(const uint32_t* p) { uint32_t v; asm volatile("ld.acquire.gpu.global.u32 %0, [%1];" : "=r"(v) : "l"(p) : "memory"); return v; }
__device__ __forceinline__ uint4 lds4(uint32_t a) { uint4 v; asm volatile("ld.shared.v4.u32 {%0,%1,%2,%3}, [%4];" : "=r"(v.x), "=r"(v.y), "=r"(v.z), "=r"(v.w) : "r"(a) : "memory"); return v; }
__device__ __forceinline__ float2 lds2f(uint32_t a) { float2 v; asm volatile("ld.shared.v2.f32 {%0,%1}, [%2];" : "=f"(v.x), "=f"(v.y) : "r"(a) : "memory"); return v; }
__device__ __forceinline__ uint32_t lds1(uint32_t a) { uint32_t v; asm volatile("ld.shared.u32 %0, [%1];" : "=r"(v) : "r"(a) : "memory"); return v; }
__device__ __forceinline__ void sts4(uint32_t a, uint4 v) { asm volatile("st.shared.v4.u32 [%0], {%1,%2,%3,%4};" ::"r"(a), "r"(v.x), "r"(v.y), "r"(v.z), "r"(v.w) : "memory"); }
__device__ __forceinline__ void sts2(uint32_t a, uint32_t x, uint32_t y) { asm volatile("st.shared.v2.u32 [%0], {%1,%2};" ::"r"(a), "r"(x), "r"(y) : "memory"); }
__device__ __forceinline__ void sts1(uint32_t a, uint32_t v) { asm volatile("st.shared.u32 [%0], %1;" ::"r"(a), "r"(v) : "memory"); }
__device__ __forceinline__ void stsm4(uint32_t a, uint32_t r0, uint32_t r1, uint32_t r2, uint32_t r3) {
    asm volatile("stmatrix.sync.aligned.m8n8.x4.shared.b16 [%0], {%1,%2,%3,%4};" ::"r"(a), "r"(r0), "r"(r1), "r"(r2), "r"(r3));
}
__device__ __forceinline__ uint32_t pack2(float lo, float hi) { uint32_t r; asm("cvt.rn.bf16x2.f32 %0, %1, %2;" : "=r"(r) : "f"(hi), "f"(lo)); return r; }
__device__ __forceinline__ uint32_t pack2_relu(float lo, float hi) { uint32_t r; asm("cvt.rn.relu.bf16x2.f32 %0, %1, %2;" : "=r"(r) : "f"(hi), "f"(lo)); return r; }
__device__ __forceinline__ uint32_t hfma2(uint32_t a, uint32_t b, uint32_t c) { uint32_t r; asm("fma.rn.bf16x2 %0, %1, %2, %3;" : "=r"(r) : "r"(a), "r"(b), "r"(c)); return r; }
__device__ __forceinline__ uint32_t hmul2(uint32_t a, uint32_t b) { uint32_t r; asm("mul.rn.bf16x2 %0, %1, %2;" : "=r"(r) : "r"(a), "r"(b)); return r; }
__device__ __forceinline__ float bf_lo(uint32_t v) { return __uint_as_float(v << 16); }
__device__ __forceinline__ float bf_hi(uint32_t v) { return __uint_as_float(v & 0xFFFF0000u); }
__device__ __forceinline__ float bf_round(float v) { return bf_lo(pack2(v, 0.f)); }
__device__ __forceinline__ float ex2(float x) { float r; asm("ex2.approx.ftz.f32 %0, %1;" : "=f"(r) : "f"(x)); return r; }
__device__ __forceinline__ void mma16816(float* d, uint32_t a0, uint32_t a1, uint32_t a2, uint32_t a3, uint32_t b0, uint32_t b1) {
    asm("mma.sync.aligned.m16n8k16.row.col.f32.bf16.bf16.f32 {%0,%1,%2,%3}, {%4,%5,%6,%7}, {%8,%9}, {%0,%1,%2,%3};"
        : "+f"(d[0]), "+f"(d[1]), "+f"(d[2]), "+f"(d[3]) : "r"(a0), "r"(a1), "r"(a2), "r"(a3), "r"(b0), "r"(b1));
}
__device__ __forceinline__ void mma16816_first(float* d, uint32_t a0, uint32_t a1, uint32_t a2, uint32_t a3, uint32_t b0, uint32_t b1) {
    asm volatile("mma.sync.aligned.m16n8k16.row.col.f32.bf16.bf16.f32 {%0,%1,%2,%3}, {%4,%5,%6,%7}, {%8,%9}, {%10,%10,%10,%10};"
        : "=f"(d[0]), "=f"(d[1]), "=f"(d[2]), "=f"(d[3]) : "r"(a0), "r"(a1), "r"(a2), "r"(a3), "r"(b0), "r"(b1), "f"(0.f));
}
__device__ __forceinline__ void mma16816_v(float* d, uint32_t a0, uint32_t a1, uint32_t a2, uint32_t a3, uint32_t b0, uint32_t b1) {
    asm volatile("mma.sync.aligned.m16n8k16.row.col.f32.bf16.bf16.f32 {%0,%1,%2,%3}, {%4,%5,%6,%7}, {%8,%9}, {%0,%1,%2,%3};"
        : "+f"(d[0]), "+f"(d[1]), "+f"(d[2]), "+f"(d[3]) : "r"(a0), "r"(a1), "r"(a2), "r"(a3), "r"(b0), "r"(b1));
}
__device__ __forceinline__ void mma1688(float* d, uint32_t a0, uint32_t a1, uint32_t b0) {
    asm("mma.sync.aligned.m16n8k8.row.col.f32.bf16.bf16.f32 {%0,%1,%2,%3}, {%4,%5}, {%6}, {%0,%1,%2,%3};"
        : "+f"(d[0]), "+f"(d[1]), "+f"(d[2]), "+f"(d[3]) : "r"(a0), "r"(a1), "r"(b0));
}
__device__ __forceinline__ void ldsm4(uint32_t a, uint32_t* r) {
    asm volatile("ldmatrix.sync.aligned.m8n8.x4.shared.b16 {%0,%1,%2,%3}, [%4];" : "=r"(r[0]), "=r"(r[1]), "=r"(r[2]), "=r"(r[3]) : "r"(a));
}
__device__ __forceinline__ void ldsm4t(uint32_t a, uint32_t* r) {
    asm volatile("ldmatrix.sync.aligned.m8n8.x4.trans.shared.b16 {%0,%1,%2,%3}, [%4];" : "=r"(r[0]), "=r"(r[1]), "=r"(r[2]), "=r"(r[3]) : "r"(a));
}
__device__ __forceinline__ float rcp(float x) { float r; asm("rcp.approx.ftz.f32 %0, %1;" : "=f"(r) : "f"(x)); return r; }
__device__ __forceinline__ uint2 ld_relaxed2(const void* p) { uint2 v; asm volatile("ld.relaxed.gpu.global.v2.u32 {%0,%1}, [%2];" : "=r"(v.x), "=r"(v.y) : "l"(p) : "memory"); return v; }
__device__ __forceinline__ void st_relaxed2(void* p, uint32_t x, uint32_t y) { asm volatile("st.relaxed.gpu.global.v2.u32 [%0], {%1,%2};" ::"l"(p), "r"(max(x, 1u)), "r"(max(y, 1u)) : "memory"); }
__device__ __forceinline__ constexpr uint64_t dconst(uint32_t lbo, uint32_t sbo, uint32_t swz) {
    return ((uint64_t)(lbo >> 4) << 16) | ((uint64_t)(sbo >> 4) << 32) | ((uint64_t)swz << 62);
}
__device__ __forceinline__ uint64_t mkdesc(uint32_t addr, uint64_t c) { return c | (uint64_t)((addr & 0x3FFFF) >> 4); }
#define WG_FENCE() asm volatile("wgmma.fence.sync.aligned;" ::: "memory")
#define WG_COMMIT() asm volatile("wgmma.commit_group.sync.aligned;" ::: "memory")
#define WG_WAIT(n) asm volatile("wgmma.wait_group.sync.aligned %0;" ::"n"(n) : "memory")
template <int N> __device__ __forceinline__ void reg_fence(float* d) {
#pragma unroll
    for (int i = 0; i < N; i++) asm volatile("" : "+f"(d[i])::"memory");
}
template <int N> __device__ __forceinline__ void reg_def(float* d) {
#pragma unroll
    for (int i = 0; i < N; i++) asm volatile("" : "=f"(d[i]));
}
template <int N> __device__ __forceinline__ void reg_def(uint32_t* d) {
#pragma unroll
    for (int i = 0; i < N; i++) asm volatile("" : "=r"(d[i]));
}
__device__ __forceinline__ bool is_unset(uint4 v) { return min(min(v.x, v.y), min(v.z, v.w)) == 0u; }
__device__ __forceinline__ uint4 nz4(uint32_t a, uint32_t b, uint32_t c, uint32_t d) { return make_uint4(max(a, 1u), max(b, 1u), max(c, 1u), max(d, 1u)); }
__device__ __forceinline__ void wait_flag(const uint32_t* p, uint32_t target) {
    int n = 0;
    while ((int)(ld_relaxed(p) - target) < 0) { if (++n > SPIN_LIMIT) __trap(); }
    asm volatile("fence.acquire.gpu;" ::: "memory");
}
__device__ __forceinline__ float silu_bf(uint32_t cbits) {
    const float c = __uint_as_float(cbits << 16);
    return bf_round(__fdividef(c, 1.f + fminf(ex2(-1.4426950408889634f * c), 1e30f)));
}
__device__ __forceinline__ void gemv_part(uint32_t wmbuf, int npanel, int wp, int lane) {
    const uint32_t wa = wmbuf + wp * 512 + (8 * (lane >> 4) + (lane & 7)) * 32 + ((lane >> 3) & 1) * 16;
    uint2 B[4];
#pragma unroll
    for (int i = 0; i < 4; i++) { const float2 v = lds2f(wmbuf + 28672 + (wp + 8 * i) * 32 + (lane & 3) * 8); B[i] = make_uint2(__float_as_uint(v.x), __float_as_uint(v.y)); }
#pragma unroll 1
    for (int pn = 0; pn < npanel; pn++) {
        float d[4] = {};
        uint32_t A[16];
#pragma unroll
        for (int i = 0; i < 4; i++) ldsm4t(wa + pn * 14336 + (i < 3 || wp < 4 ? i : 0) * 4096, A + 4 * i);
#pragma unroll
        for (int i = 0; i < 4; i++) mma16816(d, A[4 * i], A[4 * i + 1], A[4 * i + 2], A[4 * i + 3], B[i].x, B[i].y);
        if ((lane & 3) == 0) {
            sts1(wmbuf + 29696 + (wp * 32 + pn * 16 + (lane >> 2)) * 4, __float_as_uint(d[0]));
            sts1(wmbuf + 29696 + (wp * 32 + pn * 16 + 8 + (lane >> 2)) * 4, __float_as_uint(d[2]));
        }
    }
}
__device__ __forceinline__ int pass_f(int fs, int ps) { return 224 * fs + ((fs & 1) ? (ps == 0 ? 96 : ps == 1 ? 32 : 0) : (ps == 0 ? 0 : ps == 1 ? 128 : 192)); }
__device__ __forceinline__ constexpr uint32_t slot_off(int l) { return (l < 3 || l > 6 ? l : l == 6 ? 3 : l + 1) * 16384; }
__device__ __forceinline__ void ln_coeffs(float mean, float msq, uint32_t& r2, uint32_t& n2) {
    const float rs = bf_round(rsqrtf(fmaxf(msq - mean * mean, 0.f) + 1e-5f));
    r2 = pack2(rs, rs);
    n2 = pack2(-mean * rs, -mean * rs);
}

template <int sec> __device__ __forceinline__ void ring_loader(const Params& p, uint32_t sb_, int r_, int j_) {
    const uint32_t sb = opaque(sb_);
    const int r = opaque(r_), j = opaque(j_), nq = j >> 1, fs = 4 * (j & 1) + nq;
    const int fa = pass_f(fs, 0), fb = pass_f(fs, 1), fc = pass_f(fs, 2);
#define BAR(i) (sb + M_BAR + 8 * (i))
#define kh (j & 1)
            int sl = 0;
#pragma unroll 1
            for (int s = 0; s < 28; s++) {
                if (s >= 1 && s < 6) mbar_wait(BAR(B_FULL + s - 1), 0);
                const int ps = s < 14 ? 0 : s < 21 ? 1 : 2;
                const uint32_t half = ps < 2 ? 8192 : 4096;
                mbar_wait(BAR(B_EMPTY + sl), (s >= 7 && s < 14) || s >= 21);
                expect_e(BAR(B_FULL + sl), half);
                tma3_e(sb + slot_off(sl) + sec * half, &p.ga + 2 * ps + sec, 0, ps ? 64 * sl : 32 * s, ps == 0 ? fa >> 6 : ps == 1 ? fb >> 6 : fc >> 5, BAR(B_FULL + sl));
                sl = sl == 6 ? 0 : sl + 1;
            }
            if (!sec) PROFH(3);
#pragma unroll 1
            for (int e = 0; e < 4; e++) {
                const uint32_t dst = sb + slot_off(e) + sec * 8192, bar = BAR(B_FULL + e);
                const int f = (e < 2 ? fa + 64 * e : e == 2 ? fb : fc) + 32 * sec;
                mbar_wait(BAR(B_EMPTY + e), 0);
                expect_e(bar, e == 3 && sec ? 0 : 8192);
                if (!(e == 3 && sec)) { tma3_e(dst, &p.dn, 112 * nq + 48, f, 0, bar); tma3_e(dst + 4096, &p.dn, 112 * nq, f, 0, bar); }
            }
            sl = 4;
            int e = 4;
#pragma unroll 1
            for (int grp = 0; grp < 9; grp++) {
                const int ps = grp >= 6 ? 2 : grp >= 3 ? 1 : 0;
                int sidx = grp - 3 * ps;
                if (sec && sidx == 0) { mbar_wait(BAR(B_HRDY + ps), 0); fence_async_global(); }
                sidx += sidx >= nq;
                int f = pass_f(4 * kh + sidx, ps);
#pragma unroll 1
                for (int k = 4 >> ps; k > 0; k--, e++, f += 32) {
                    const uint32_t dst = sb + slot_off(sl), bar = BAR(B_FULL + sl);
                    mbar_wait(BAR(B_EMPTY + sl), e >= 12 && e < 24);
                    if (e < WIN_END) mbar_wait(BAR(B_FULL + (sl >= WIN ? sl - WIN : sl + 12 - WIN)), e - WIN >= 12);
                    expect_e(bar, 8192);
                    if (!sec) { tma3_e(dst, &p.dn, 112 * nq + 48, f, 0, bar); tma3_e(dst + 4096, &p.dn, 112 * nq, f, 0, bar); }
                    else bulk_e(dst + 8192, g_h2 + (size_t)r * (224 * 512) + f * 64, 8192, bar);
                    sl = sl == 11 ? 0 : sl + 1;
                }
            }
            if (!sec) PROFH(4);
}

__global__ void __cluster_dims__(2, 1, 1) __launch_bounds__(384, 1) fused_block_kernel(const __grid_constant__ Params p) {
    extern __shared__ __align__(1024) unsigned char smem[];
    const uint32_t sb = (uint32_t)__cvta_generic_to_shared(smem);
    const int tid = threadIdx.x, lane = tid & 31, warp = __shfl_sync(~0u, tid >> 5, 0);
    const int m = blockIdx.x >> 1;
    int r, nq;
    {
        int g, i;
        if (m < MAP_S) { g = m < 4 ? 15 : 16; i = m & 3; }
        else if (m < MAP_S + 32) { g = (m - MAP_S) & 7; i = (m - MAP_S) >> 3; }
        else if (m < MAP_S + 60) { i = (m - MAP_S - 32) / 7; g = 8 + (m - MAP_S - 32) - 7 * i; }
        else { g = 16; i = m & 3; }
        r = g; nq = i;
    }
    const int j = opaque(2 * nq + (blockIdx.x & 1)), b = 8 * r + j, fs = 4 * kh + nq;
    const uint32_t sc = r == 16;
    if (lane == 0 && warp < 9 && warp != 6 && warp != 7) {
        const int i0 = warp == 8 ? 0 : 8 + 8 * warp, cnt = warp == 0 || warp == 8 ? 1 : warp < 3 ? 2 : 8;
#pragma unroll
        for (int k = 0; k < 8; k++) if (i0 + k != B_WMFULL) mbar_init(BAR(i0 + k), cnt);
        asm volatile("fence.mbarrier_init.release.cluster;" ::: "memory");
        fence_async_smem();
    }

    if (warp < 8) {
        const int w = warp >> 2, wi = warp & 3;
#define COORDS const int t = fresh_tid() & 127, lane = t & 31, q = lane & 3, lr = lane >> 2, ra = 64 * w + 16 * wi + lr; \
        const uint32_t lx = (lane >> 4) ^ (lane & 7), mrow = (64 * w + 16 * wi + ((lane >> 3) & 1) * 8 + (lane & 7)) * 128; \
        (void)q; (void)lr; (void)ra; (void)lx; (void)mrow;
        const int sid = 2 * (j & 3) + w;
#define RUN(k) (!sc || sid == (k))
#define WAIT(i, par) mbar_wait(BAR(i), (par) | sc)
        constexpr uint64_t DB128 = dconst(4096, 1024, 1);
        bar_arrive(9, 384);
        bar_sync(0, 384);
        asm volatile("barrier.cluster.arrive.relaxed.aligned;" ::: "memory");
        asm volatile("setmaxnreg.inc.sync.aligned.u32 224;");
        PROFC(0);
        uint32_t xr[16];
        {
            COORDS
            uint32_t h[112];
            if (RUN(0)) {
                float ds[4] = {}, da[2][4] = {}, db[2][4] = {};
                const uint32_t ONE2 = 0x3F803F80u;
                if (kh == 0) { WAIT(B_WMFULL, 0); gemv_part(sb + OFF_Y + HALF, 1, warp, lane); warp_arrive(BAR(B_GEMV)); }
#pragma unroll
                for (int kb = 0; kb < 7; kb++) {
                    WAIT(B_XFULL + kb, 0);
#pragma unroll
                    for (int k4 = 0; k4 < 4; k4++) ldsm4(sb + OFF_X + mrow + kb * 16384 + (((2 * k4) ^ lx) << 4), h + 16 * kb + 4 * k4);
#pragma unroll
                    for (int k4 = 0; k4 < 4; k4++) {
                        const uint32_t* f = h + 16 * kb + 4 * k4;
                        mma16816(ds, f[0], f[1], f[2], f[3], ONE2, ONE2);
                        mma1688(da[0], f[0], f[1], f[0]); mma1688(db[0], f[0], f[1], f[1]);
                        mma1688(da[1], f[2], f[3], f[2]); mma1688(db[1], f[2], f[3], f[3]);
                    }
                }
#pragma unroll
                for (int i = 0; i < 4; i++) {
                    const int ch = 7 * j + 2 * i + (lane >> 4);
                    ldsm4(sb + OFF_X + mrow + (ch >> 3) * 16384 + (((ch ^ lane) & 7) << 4), xr + 4 * i);
                }
                warp_arrive(BAR(B_XFREE));
                float qa = (lr & 1) ? da[0][1] + da[1][1] : da[0][0] + da[1][0];
                float qb = (lr & 1) ? db[0][3] + db[1][3] : db[0][2] + db[1][2];
                const int src = (lane & ~3) | (lr >> 1);
                qa = __shfl_sync(~0u, qa, src);
                qb = __shfl_sync(~0u, qb, src);
                uint32_t ra2, na2, rb2, nb2;
                ln_coeffs(ds[0] * (1.f / DM), qa * (1.f / DM), ra2, na2);
                ln_coeffs(ds[2] * (1.f / DM), qb * (1.f / DM), rb2, nb2);
#pragma unroll
                for (int i = 0; i < 112; i += 2) { h[i] = hfma2(h[i], ra2, na2); h[i + 1] = hfma2(h[i + 1], rb2, nb2); }
                if (kh == 1) { WAIT(B_WMFULL, 0); gemv_part(sb + OFF_Y + HALF, 2, warp, lane); warp_arrive(BAR(B_GEMV)); }
            } else { reg_def<112>(h); reg_def<16>(xr); }
            PROFC(1);
            if (RUN(1)) {
                float ak[28], av[28], aq[28];
                uint32_t kp[14], vp[14];
                const uint64_t bk0 = mkdesc(sb + OFF_Y, DB128) + kh, bv0 = mkdesc(sb + OFF_Y + HALF, DB128) + kh, bq0 = mkdesc(sb + OFF_X, DB128) + kh;
                uint32_t* kvg = g_kv + (size_t)(b * 2) * 3584 + (8 * w + 2 * wi) * 224 + lane;
                WAIT(B_FULLK, 0);
                WAIT(B_MOD1, 0);
                PROFC(2);
                reg_def<28>(ak);
#pragma unroll
                for (int g4 = 0; g4 < 4; g4++) {
#pragma unroll
                    for (int ks = 7 * g4; ks < 7 * g4 + 7; ks++) {
                        const uint4 st = *(const uint4*)(smem + M_ST + ks * 64 + q * 16);
                        h[4 * ks] = hfma2(h[4 * ks], st.x, st.y); h[4 * ks + 1] = hfma2(h[4 * ks + 1], st.x, st.y);
                        h[4 * ks + 2] = hfma2(h[4 * ks + 2], st.z, st.w); h[4 * ks + 3] = hfma2(h[4 * ks + 3], st.z, st.w);
                    }
                    WG_FENCE();
#pragma unroll
                    for (int ks = 7 * g4; ks < 7 * g4 + 7; ks++) wgmma_rs_56<1>(ak, h[4 * ks], h[4 * ks + 1], h[4 * ks + 2], h[4 * ks + 3], bk0 + ks * 128, ks != 0);
                }
                WG_COMMIT();
                PROFC(3);
                WAIT(B_FULLV, 0);
                reg_def<28>(av);
                WG_FENCE();
#pragma unroll
                for (int ks = 0; ks < 8; ks++) wgmma_rs_56<1>(av, h[4 * ks], h[4 * ks + 1], h[4 * ks + 2], h[4 * ks + 3], bv0 + ks * 128, ks != 0);
                WG_COMMIT();
                WG_WAIT(1);
                reg_fence<28>(ak);
#pragma unroll
                for (int g = 0; g < 7; g++) {
                    kp[2 * g] = pack2(ak[4 * g], ak[4 * g + 1]); kp[2 * g + 1] = pack2(ak[4 * g + 2], ak[4 * g + 3]);
                    kvg[g * 32] = kp[2 * g]; kvg[224 + g * 32] = kp[2 * g + 1];
                }
                warp_arrive(BAR(B_PUB));
                PROFC(4);
                WG_FENCE();
#pragma unroll
                for (int ks = 8; ks < 28; ks++) wgmma_rs_56<1>(av, h[4 * ks], h[4 * ks + 1], h[4 * ks + 2], h[4 * ks + 3], bv0 + ks * 128, 1);
                WG_COMMIT();
                WAIT(B_FULLQ, 0);
                reg_def<28>(aq);
                WG_FENCE();
#pragma unroll
                for (int ks = 0; ks < 8; ks++) wgmma_rs_56<1>(aq, h[4 * ks], h[4 * ks + 1], h[4 * ks + 2], h[4 * ks + 3], bq0 + ks * 128, ks != 0);
                WG_COMMIT();
                WG_WAIT(1);
                reg_fence<28>(av);
#pragma unroll
                for (int g = 0; g < 7; g++) {
                    vp[2 * g] = pack2(av[4 * g], av[4 * g + 1]); vp[2 * g + 1] = pack2(av[4 * g + 2], av[4 * g + 3]);
                    kvg[3584 + g * 32] = vp[2 * g]; kvg[3584 + 224 + g * 32] = vp[2 * g + 1];
                }
                warp_arrive(BAR(B_PUB + 1));
                PROFC(5);
                WG_FENCE();
#pragma unroll
                for (int ks = 8; ks < 28; ks++) wgmma_rs_56<1>(aq, h[4 * ks], h[4 * ks + 1], h[4 * ks + 2], h[4 * ks + 3], bq0 + ks * 128, 1);
                WG_COMMIT();
                WAIT(B_PUB + 1, 0);
                const uint32_t ko = sb + OFF_Y + Y_KOWN + (8 * w + 2 * wi) * 896 + lane * 4;
                const uint32_t qo = sb + OFF_Y + Y_Q + (8 * w + 2 * wi) * 1024 + lane * 4;
#pragma unroll
                for (int g = 0; g < 7; g++) {
                    sts1(ko + g * 128, kp[2 * g]); sts1(ko + 896 + g * 128, kp[2 * g + 1]);
                    sts1(ko + (Y_VOWN - Y_KOWN) + g * 128, vp[2 * g]); sts1(ko + (Y_VOWN - Y_KOWN) + 896 + g * 128, vp[2 * g + 1]);
                }
                WG_WAIT(0);
                reg_fence<28>(aq);
                __syncwarp();
                if (lane < 3 && w == 1) mbar_arrive(BAR(B_EMPTY + lane));
#pragma unroll
                for (int g = 0; g < 7; g++) {
                    const uint32_t q0 = pack2(aq[4 * g], aq[4 * g + 1]), q1 = pack2(aq[4 * g + 2], aq[4 * g + 3]);
                    if (g == 3) {
                        sts1(qo + 3 * 128, q < 2 ? q0 : 0u); sts1(qo + 1024 + 3 * 128, q < 2 ? q1 : 0u);
                        sts1(qo + 4 * 128, q < 2 ? 0u : q0); sts1(qo + 1024 + 4 * 128, q < 2 ? 0u : q1);
                    } else {
                        const int ch = g < 3 ? g : g + 1;
                        sts1(qo + ch * 128, q0); sts1(qo + 1024 + ch * 128, q1);
                    }
                }
                if (!sc) bar_sync(3, 256);
            }
        }
        PROFC(6);
        WAIT(B_KRFULL, 0);
        PROFC(7);
        if (RUN(2)) {
#pragma unroll 1
            for (int hf = sc; hf < 2; hf++) {
                COORDS
                float s[136];
                float na = 0.f, nb = 0.f;
                const float CS = 0.18898223650461361f * 1.4426950408889634f;
                const int kg0 = 8 * hf + 2 * wi;
                const int pmin = 16 - 8 * r - 4 * hf - wi;
                const float NEG = __int_as_float(0xFF800000);
                {
                    uint32_t F[8];
                    const uint32_t qa = sb + OFF_Y + Y_Q + (kg0 + ((lane >> 3) & 1)) * 1024 + (4 * w + (lane >> 4)) * 128 + (lane & 7) * 16;
                    ldsm4(qa, F); ldsm4(qa + 256, F + 4);
                    uint32_t ka = sb + OFF_Y + Y_K + kg0 * 896 + (3 * w + (lane >> 3)) * 128 + (lane & 7) * 16;
#pragma unroll
                    for (int g = 0; g < 34; g++) {
                        uint32_t B[4];
                        if (g >= 12 && g % 4 == 0) ka += __float_as_uint(s[4 * (g - 12)]) & p.zero;
                        ldsm4(ka + g * 896, B);
                        mma16816_first(s + 4 * g, F[0], F[1], F[2], F[3], B[0], B[1]);
                        mma16816_v(s + 4 * g, F[4], F[5], F[6], F[7], B[2], B[3]);
                    }
                    const bool c0 = 2 * q > lr, c1 = 2 * q + 1 > lr;
                    if (!c0) { s[0] = NEG; s[6] = NEG; }
                    if (!c1) { s[1] = NEG; s[7] = NEG; }
                    s[2] = NEG; s[3] = NEG;
                    if (c0) { s[128] = NEG; s[134] = NEG; }
                    if (c1) { s[129] = NEG; s[135] = NEG; }
                    s[132] = NEG; s[133] = NEG;
                    float ma = NEG, mb = NEG;
#pragma unroll
                    for (int pp = 0; pp < 17; pp++) {
                        const float* e = s + 8 * pp;
                        const float bias = pp < pmin ? NEG : 0.f;
                        ma = fmaxf(ma, fmaxf(fmaxf(e[0], e[1]), fmaxf(e[4], e[5])) + bias);
                        mb = fmaxf(mb, fmaxf(fmaxf(e[2], e[3]), fmaxf(e[6], e[7])) + bias);
                    }
                    ma = fmaxf(ma, __shfl_xor_sync(~0u, ma, 1)); mb = fmaxf(mb, __shfl_xor_sync(~0u, mb, 1));
                    ma = fmaxf(ma, __shfl_xor_sync(~0u, ma, 2)); mb = fmaxf(mb, __shfl_xor_sync(~0u, mb, 2));
                    na = -ma * CS; nb = -mb * CS;
                }
                PROFC(8 + 3 * hf);
                {
                    if (hf == 0) mbar_wait(BAR(B_VRFULL), 0);
                    float o[16] = {}, rs[4] = {};
                    const uint32_t va = sb + OFF_Y + Y_VR + (kg0 + ((lane >> 3) & 1)) * 896 + (3 * w + (lane >> 4)) * 128 + (lane & 7) * 16;
#pragma unroll
                    for (int pp = 0; pp < 17; pp++) {
                        uint32_t B[8];
                        const uint32_t v = va + pp * 1792 + (pp == 16 || (pp >= 9 && kg0 + 2 * pp >= 32) ? Y_VOWN - 32 * 896 : 0);
                        ldsm4t(v, B); ldsm4t(v + 256, B + 4);
                        float e[8];
#pragma unroll
                        for (int i = 0; i < 8; i++) e[i] = ex2(fmaf(s[8 * pp + i], CS, ((i & 2) ? nb : na) + (pp < pmin ? NEG : 0.f)));
                        const uint32_t p0 = pack2(e[0], e[1]), p1 = pack2(e[2], e[3]), p2 = pack2(e[4], e[5]), p3 = pack2(e[6], e[7]);
                        mma16816(rs, p0, p1, p2, p3, 0x3F803F80u, 0x3F803F80u);
#pragma unroll
                        for (int g = 0; g < 4; g++) mma16816(o + 4 * g, p0, p1, p2, p3, B[2 * g], B[2 * g + 1]);
                    }
                    PROFC(9 + 3 * hf);
                    const float ia = rcp(rs[0]), ib = rcp(rs[2]);
                    uint32_t* og = g_o + (size_t)(2 * r + hf) * 14336 + (7 * j + 3 * w) * 256 + wi * 64 + lane;
#pragma unroll
                    for (int g = 0; g < 4; g++) {
                        if ((g == 3 - 3 * w) ? ((q >> 1) == w) : true) {
                            og[g * 256] = pack2(o[4 * g] * ia, o[4 * g + 1] * ia);
                            og[g * 256 + 32] = pack2(o[4 * g + 2] * ib, o[4 * g + 3] * ib);
                        }
                    }
                    warp_arrive(BAR(B_PUB + 2 + hf));
                    PROFC(10 + 3 * hf);
                }
            }
        }
        uint32_t x1p[14];
        COORDS
        constexpr uint64_t DT = dconst(1024, 128, 0);
        if (RUN(4)) {
            float ac[28];
            const uint64_t ad = mkdesc(sb + (w ? OFF_Y + HALF : OFF_X), DT), bd = mkdesc(sb + OFF_X + HALF, DB128) + kh;
            WAIT(B_WOFULL, 0);
            WAIT(B_MOD2, 0);
            WAIT(B_GFULL + w, 0);
            PROFC(28);
            reg_def<28>(ac);
#pragma unroll 1
            for (int u = 0; u < 4; u++) {
                WG_FENCE();
#pragma unroll
                for (int i = 0; i < 7; i++) wgmma_ss_56<1>(ac, ad + (7 * u + i) * 128, bd + (7 * u + i) * 128, (u | i) != 0);
            }
            WG_COMMIT();
            WG_WAIT(0);
            reg_fence<28>(ac);
            PROFC(14);
            __syncwarp();
            if (lane < 3) mbar_arrive(BAR(B_EMPTY + 3 + lane));
            if (lane < 3 && w == 0) mbar_arrive(BAR(B_EMPTY + lane));
            float s1a = 0.f, s2a = 0.f, s1b = 0.f, s2b = 0.f;
            uint32_t* xo = g_x1 + (size_t)(2 * r + w) * 14336 + 7 * j * 256 + wi * 64 + lane;
#pragma unroll
            for (int g = 0; g < 7; g++) {
                const float2 ga = *(const float2*)(smem + M_G + (8 * g + 2 * q) * 4);
                x1p[2 * g] = pack2(fmaf(ga.x, ac[4 * g], bf_lo(xr[2 * g])), fmaf(ga.y, ac[4 * g + 1], bf_hi(xr[2 * g])));
                x1p[2 * g + 1] = pack2(fmaf(ga.x, ac[4 * g + 2], bf_lo(xr[2 * g + 1])), fmaf(ga.y, ac[4 * g + 3], bf_hi(xr[2 * g + 1])));
                xo[g * 256] = x1p[2 * g]; xo[g * 256 + 32] = x1p[2 * g + 1];
                const float u0 = bf_lo(x1p[2 * g]), u1 = bf_hi(x1p[2 * g]), u2 = bf_lo(x1p[2 * g + 1]), u3 = bf_hi(x1p[2 * g + 1]);
                s1a += u0 + u1; s2a += u0 * u0 + u1 * u1; s1b += u2 + u3; s2b += u2 * u2 + u3 * u3;
            }
            float ka = (q & 1) ? s2a : s1a, kb2 = (q & 1) ? s2b : s1b;
            ka += __shfl_xor_sync(~0u, (q & 1) ? s1a : s2a, 1); kb2 += __shfl_xor_sync(~0u, (q & 1) ? s1b : s2b, 1);
            const float kk = ((q & 2) ? kb2 : ka) + __shfl_xor_sync(~0u, (q & 2) ? ka : kb2, 2);
            ((float*)g_st)[(((2 * r + w) * 8 + j) * 64 + 16 * wi + lr + 4 * (q & 2)) * 2 + (q & 1)] = kk;
            __syncwarp();
            if (lane < 2) mbar_arrive(BAR(B_PUB + 4 + w));
        } else reg_def<14>(x1p);
        PROFC(15);
        uint32_t h2a[32], h2b[24];
        if (RUN(6)) {
            const int fa = pass_f(fs, 0), fb = pass_f(fs, 1), fc = pass_f(fs, 2);
            uint32_t* h2g = g_h2 + (size_t)r * (224 * 512) + (8 * w + 2 * wi) * 32 + lane;
            const uint64_t a0 = mkdesc(sb + OFF_Y + w * HALF, DT);
            const int s0 = sc ? 12 : 0;
            {
                WAIT(B_GFULL + 2 + w, 0);
                PROFC(16);
                float2 sa = make_float2(0.f, 0.f), sbb = sa;
#pragma unroll
                for (int jj = 0; jj < 8; jj++) {
                    const float2 u = lds2f(sb + OFF_X + X_STAT + w * 4096 + (jj * 64 + 16 * wi + lr) * 8), v = lds2f(sb + OFF_X + X_STAT + w * 4096 + (jj * 64 + 16 * wi + lr + 8) * 8);
                    sa.x += u.x; sa.y += u.y; sbb.x += v.x; sbb.y += v.y;
                }
                warp_arrive(BAR(B_EMPTY + 6));
                uint32_t ra2, na2, rb2, nb2;
                ln_coeffs(sa.x * (1.f / DM), sa.y * (1.f / DM), ra2, na2);
                ln_coeffs(sbb.x * (1.f / DM), sbb.y * (1.f / DM), rb2, nb2);
                const uint32_t ha = sb + OFF_Y + w * HALF + (lane >> 4) * 1024 + (2 * wi + ((lane >> 3) & 1)) * 128 + (lane & 7) * 16;
                const uint32_t sta = sb + M_ST + q * 16;
                auto prep = [&](int s, uint32_t* f) {
                    uint32_t x[8];
                    ldsm4(ha + s * 4096, x); ldsm4(ha + s * 4096 + 2048, x + 4);
                    const uint4 st[2] = {lds4(sta + s * 128), lds4(sta + s * 128 + 64)};
#pragma unroll
                    for (int i = 0; i < 2; i++) {
                        f[4 * i] = hfma2(hfma2(x[4 * i], ra2, na2), st[i].x, st[i].y); f[4 * i + 1] = hfma2(hfma2(x[4 * i + 1], rb2, nb2), st[i].x, st[i].y);
                        f[4 * i + 2] = hfma2(hfma2(x[4 * i + 2], ra2, na2), st[i].z, st[i].w); f[4 * i + 3] = hfma2(hfma2(x[4 * i + 3], rb2, nb2), st[i].z, st[i].w);
                    }
                    stsm4(ha + s * 4096, f[0], f[1], f[2], f[3]); stsm4(ha + s * 4096 + 2048, f[4], f[5], f[6], f[7]);
                };
                float ac[128];
                uint32_t fr[3][8];
                const uint64_t bx = mkdesc(sb, DB128);
                reg_def<128>(ac);
                prep(0, fr[0]);
                PROFC(17);
#pragma unroll
                for (int s = 0; s < 14; s++) {
                    const uint32_t* f = fr[s % 3];
                    const uint64_t bd = bx + (slot_off(s % 7) >> 4);
                    WAIT(B_FULL + s % 7, s >= 7);
                    WG_FENCE();
                    wgmma_rs_256<1>(ac, f[0], f[1], f[2], f[3], bd, s != 0);
                    wgmma_rs_256<1>(ac, f[4], f[5], f[6], f[7], bd + 128, 1);
                    WG_COMMIT();
                    if (s < 13) prep(s + 1, fr[(s + 1) % 3]);
                    if (s > 0) { WG_WAIT(1); warp_arrive(BAR(B_EMPTY + (s - 1) % 7)); }
                }
                fence_async_smem();
                WG_WAIT(0);
                reg_fence<128>(ac);
                warp_arrive(BAR(B_EMPTY + 6));
                PROFC(18);
#pragma unroll
                for (int g = 0; g < 16; g++) {
                    h2a[2 * g] = hmul2(pack2_relu(ac[4 * g], ac[4 * g + 1]), pack2(ac[64 + 4 * g], ac[64 + 4 * g + 1]));
                    h2a[2 * g + 1] = hmul2(pack2_relu(ac[4 * g + 2], ac[4 * g + 3]), pack2(ac[64 + 4 * g + 2], ac[64 + 4 * g + 3]));
                    h2g[(fa / 8 + g) * 512] = h2a[2 * g]; h2g[(fa / 8 + g) * 512 + 32] = h2a[2 * g + 1];
                }
                warp_arrive(BAR(B_PUB + 6));
                bar_sync(1 + w, 128);
            }
            PROFC(19);
            {
                float ac[64];
                reg_def<64>(ac);
#pragma unroll 1
                for (int s = s0 >> 1; s < 7; s++) {
                    WAIT(B_FULL + s, 0);
                    const uint64_t ad = a0 + s * 512, bd = mkdesc(sb + slot_off(s), dconst(8192, 1024, 1));
                    WG_FENCE();
#pragma unroll
                    for (int k = 0; k < 4; k++) wgmma_ss_128<1>(ac, ad + k * 128, bd + k * 128, (s | k) != 0);
                    WG_COMMIT();
                    if (s > 0) { WG_WAIT(1); warp_arrive(BAR(B_EMPTY + s - 1)); }
                }
                WG_WAIT(0);
                reg_fence<64>(ac);
                warp_arrive(BAR(B_EMPTY + 6));
#pragma unroll
                for (int g = 0; g < 8; g++) {
                    h2b[2 * g] = hmul2(pack2_relu(ac[4 * g], ac[4 * g + 1]), pack2(ac[32 + 4 * g], ac[32 + 4 * g + 1]));
                    h2b[2 * g + 1] = hmul2(pack2_relu(ac[4 * g + 2], ac[4 * g + 3]), pack2(ac[32 + 4 * g + 2], ac[32 + 4 * g + 3]));
                    h2g[(fb / 8 + g) * 512] = h2b[2 * g]; h2g[(fb / 8 + g) * 512 + 32] = h2b[2 * g + 1];
                }
                warp_arrive(BAR(B_PUB + 7));
            }
            PROFC(27);
            {
                float ac[32];
                reg_def<32>(ac);
#pragma unroll 1
                for (int s = s0 >> 1; s < 7; s++) {
                    WAIT(B_FULL + s, 1);
                    const uint64_t ad = a0 + s * 512, bd = mkdesc(sb + slot_off(s), dconst(4096, 512, 2));
                    WG_FENCE();
#pragma unroll
                    for (int k = 0; k < 4; k++) wgmma_ss_64<1>(ac, ad + k * 128, bd + k * 64, (s | k) != 0);
                    WG_COMMIT();
                    if (s > 0) { WG_WAIT(1); warp_arrive(BAR(B_EMPTY + s - 1)); }
                }
                WG_WAIT(0);
                reg_fence<32>(ac);
                __syncwarp();
                if (lane < 6) mbar_arrive(BAR(B_EMPTY + 6 + lane));
                PROFC(20);
#pragma unroll
                for (int g = 0; g < 4; g++) {
                    h2b[16 + 2 * g] = hmul2(pack2_relu(ac[4 * g], ac[4 * g + 1]), pack2(ac[16 + 4 * g], ac[16 + 4 * g + 1]));
                    h2b[16 + 2 * g + 1] = hmul2(pack2_relu(ac[4 * g + 2], ac[4 * g + 3]), pack2(ac[16 + 4 * g + 2], ac[16 + 4 * g + 3]));
                    h2g[(fc / 8 + g) * 512] = h2b[16 + 2 * g]; h2g[(fc / 8 + g) * 512 + 32] = h2b[16 + 2 * g + 1];
                }
                warp_arrive(BAR(B_PUB + 8));
                asm volatile("barrier.cluster.wait.aligned;" ::: "memory");
                if (lane == 0 && !sc) {
                    uint32_t rb;
                    asm volatile("mapa.shared::cluster.u32 %0, %1, %2;" : "=r"(rb) : "r"(BAR(B_PEER)), "r"(kh ^ 1));
                    asm volatile("mbarrier.arrive.relaxed.cluster.shared::cluster.b64 _, [%0];" ::"r"(rb) : "memory");
                }
            }
        } else { reg_def<32>(h2a); reg_def<24>(h2b); }
        PROFC(21);
        if (RUN(7)) {
            float ac[56];
            reg_def<56>(ac);
            constexpr uint64_t DAN = dconst(2048, 128, 0);
#pragma unroll
            for (int e = 0; e < 4; e++) {
                WAIT(B_FULL + e, 0);
                const uint64_t bd = mkdesc(sb + slot_off(e), DB128);
                const uint32_t* hh = e < 2 ? h2a + 16 * e : h2b + 16 * (e - 2);
                WG_FENCE();
#pragma unroll
                for (int k = 0; k < (e < 3 ? 4 : 2); k++) wgmma_rs_112<1>(ac, hh[4 * k], hh[4 * k + 1], hh[4 * k + 2], hh[4 * k + 3], bd + (k >> 1) * 512 + (k & 1) * 128, (e | k) != 0);
                WG_COMMIT();
                if (e > 0) { WG_WAIT(1); warp_arrive(BAR(B_EMPTY + e - 1)); }
            }
            PROFC(22);
            int sl = 4, prev = 3;
#pragma unroll 1
            for (int e = 4; e < 25; e++) {
                WAIT(B_FULL + sl, e >= 12 && e < 24);
                if (e == 16) PROFC(23);
                const uint32_t sa = sb + slot_off(sl);
                const uint64_t ad = mkdesc(sa + 8192 + w * 1024, DAN), bd = mkdesc(sa, DB128);
                WG_FENCE();
                wgmma_ss_112<1>(ac, ad, bd, 1);
                wgmma_ss_112<1>(ac, ad + 256, bd + 128, 1);
                WG_COMMIT();
                if (e < 14) { WG_WAIT(1); warp_arrive(BAR(B_EMPTY + prev)); }
                prev = sl; sl = sl == 11 ? 0 : sl + 1;
            }
            mbar_wait_cluster(BAR(B_PEER), sc);
            WG_WAIT(0);
            reg_fence<56>(ac);
            PROFC(24);
            uint32_t rdst, rbar;
            asm volatile("mapa.shared::cluster.u32 %0, %1, %2;" : "=r"(rdst) : "r"(sb + OFF_Y + (5 + w) * 16384 + t * 16), "r"(kh ^ 1 ^ sc));
            asm volatile("mapa.shared::cluster.u32 %0, %1, %2;" : "=r"(rbar) : "r"(BAR(B_XCH + w)), "r"(kh ^ 1 ^ sc));
#define ACG(g, i) ac[4 * (((g) + 8) % 14) + (i)]
#pragma unroll
            for (int g = 0; g < 7; g++) {
                const float v0 = kh ? ACG(g, 0) : ACG(g + 7, 0), v1 = kh ? ACG(g, 1) : ACG(g + 7, 1);
                const float v2 = kh ? ACG(g, 2) : ACG(g + 7, 2), v3 = kh ? ACG(g, 3) : ACG(g + 7, 3);
                if (!sc) asm volatile("st.async.shared::cluster.mbarrier::complete_tx::bytes.v4.f32 [%0], {%1,%2,%3,%4}, [%5];"
                             ::"r"(rdst + g * 2048), "f"(v0), "f"(v1), "f"(v2), "f"(v3), "r"(rbar) : "memory");
            }
            mbar_wait_cluster(BAR(B_XCH + w), sc);
            PROFC(25);
            bf16* og = (sc ? (bf16*)(g_h2 + 16 * 224 * 512) : p.out + (size_t)128 * r * DM) + (size_t)ra * DM + 56 * j + 2 * q;
#pragma unroll
            for (int g = 0; g < 7; g++) {
                const uint4 rv = *(const uint4*)(smem + OFF_Y + (5 + w) * 16384 + t * 16 + g * 2048);
                const float2 gb = *(const float2*)(smem + M_G + 224 + (8 * g + 2 * q) * 4);
                const float v0 = (kh ? ACG(g + 7, 0) : ACG(g, 0)) + __uint_as_float(rv.x), v1 = (kh ? ACG(g + 7, 1) : ACG(g, 1)) + __uint_as_float(rv.y);
                const float v2 = (kh ? ACG(g + 7, 2) : ACG(g, 2)) + __uint_as_float(rv.z), v3 = (kh ? ACG(g + 7, 3) : ACG(g, 3)) + __uint_as_float(rv.w);
                *(uint32_t*)(og + 8 * g) = pack2(fmaf(gb.x, v0, bf_lo(x1p[2 * g])), fmaf(gb.y, v1, bf_hi(x1p[2 * g])));
                *(uint32_t*)(og + 8 * DM + 8 * g) = pack2(fmaf(gb.x, v2, bf_lo(x1p[2 * g + 1])), fmaf(gb.y, v3, bf_hi(x1p[2 * g + 1])));
            }
        }
        PROFC(26);
        bar_sync(1 + w, 128);
        if (wi == 0) warp_arrive(BAR(B_DONE));
    } else {
        const int lane = fresh_tid() & 31;
        const bool early = kh == 0, gemv = r < 14;
        const int mcol = early ? 16 * (4 * r + nq) : 2 * DM + 32 * (4 * r + nq);
        const uint32_t wmbuf = sb + OFF_Y + HALF;
        asm volatile("setmaxnreg.dec.sync.aligned.u32 56;");
        if (warp == 9) {
#pragma unroll
            for (int i = 56; i < 64; i++) init_e(BAR(i), 1);
            fence_async_smem();
        }
        if (warp == 8) { init_e(BAR(B_WMFULL), 2); fence_async_smem(); }
        bar_arrive(0, 384);
        asm volatile("barrier.cluster.arrive.relaxed.aligned;" ::: "memory");
        uint32_t target = 0;
        if (warp == 8) {
            if (!sc) {
                expect_e(BAR(B_WMFULL), gemv ? 28672 >> early : 0);
                if (early && gemv) { tma3_e(wmbuf, &p.wm, mcol, 0, 0, BAR(B_WMFULL)); tma3_e(wmbuf + 7168, &p.wm, mcol, 224, 0, BAR(B_WMFULL)); }
#pragma unroll 1
                for (int kb = 0; kb < 7; kb++) {
                    expect_e(BAR(B_XFULL + kb), 16384);
                    tma3_e(sb + OFF_X + kb * 16384, &p.xm, 64 * kb, 128 * r, 0, BAR(B_XFULL + kb));
                }
            }
#pragma unroll 1
            for (int mt = 0; mt < 4; mt++) {
                if (mt == 1) {
                    if (!early && gemv) {
#pragma unroll 1
                        for (int k = 0; k < 4; k++) tma3_e(wmbuf + k * 7168, &p.wm, mcol + (k >> 1) * 16, (k & 1) * 224, 0, BAR(B_WMFULL));
                    }
                    bar_sync(9, 384);
                    if (sc) return;
                    mbar_wait(BAR(B_MOD1), 0);
                    mbar_wait(BAR(B_WMFREE), 0);
                }
                if (mt == 2) mbar_wait(BAR(B_XFREE), 0);
                if (mt == 3) mbar_wait(BAR(B_VRFULL), 0);
                const uint32_t bar = BAR(mt == 3 ? B_WOFULL : B_FULLK + mt), dst = sb + (mt < 2 ? OFF_Y : OFF_X) + (mt & 1) * HALF;
                const int c0 = (mt < 2 ? DM + DM * mt : 0) + 56 * j - 8 * kh;
                if (!sc) {
                    expect_e(bar, HALF);
                    tma3_e(dst, mt == 3 ? &p.wo : &p.qkv, c0, 0, 0, bar);
                    tma3_e(dst + HALF / 2, mt == 3 ? &p.wo : &p.qkv, c0, 224, 0, bar);
                }
            }
            expect_e(BAR(B_XCH), 14336);
            expect_e(BAR(B_XCH + 1), 14336);
        } else {
            if (warp == 10 && !sc) {
                l2_prefetch_e((const char*)p.wqkv + (size_t)b * 9408, 9408);
                if (lane == 0) sts1(sb + M_EPOCH, atomicAdd(&g_ticket, 1u) / NCTA);
            }
            if (warp == 11) {
#pragma unroll
                for (int i = 0; i < 8; i++) {
                    const int wd = lane + 32 * i;
                    const uint32_t cb = i < 7 ? __ldg((const uint32_t*)p.c + wd) : 0u;
                    sts1(wmbuf + 28672 + (wd >> 3) * 32 + (wd & 3) * 8 + (wd & 4), pack2(silu_bf(cb & 0xFFFFu), silu_bf(cb >> 16)));
                }
            }
            bar_sync(9, 384);
            if (sc) return;
            target = lds1(sb + M_EPOCH) + 1;
            const uint32_t tag = target & 0xFFFFu;
            if (warp == 11) {
                warp_arrive(BAR(B_WMFULL));
                mbar_wait(BAR(B_GEMV), 0);
                float sum = 0.f;
#pragma unroll
                for (int i = 0; i < 8; i++) sum += *(const float*)(smem + OFF_Y + HALF + 29696 + (i * 32 + (early ? lane & 15 : lane)) * 4);
                const uint32_t word = (pack2(sum, 0.f) << 16) | tag;
                if (gemv) {
                    uint32_t* mg = g_mod + mcol + (early ? (lane & 15) + (lane >> 4) * 4 * 6 * DM : lane);
#pragma unroll
                    for (int i = 0; i < 8; i++) if (i < 4 || !early) st_relaxed(mg + i * 6 * DM, word);
                }
                warp_arrive(BAR(B_WMFREE));
            }
            const uint4* modp = (const uint4*)g_mod + (r & 7) * (6 * DM / 4);
            const bool p2 = warp == 11;
            mbar_wait(BAR(p2 ? B_PUB : B_XFULL + 4), 0);
#pragma unroll 1
            for (int it = p2 ? 0 : warp - 9; it < (p2 ? 2 : warp - 8); it++) {
                const int i0 = lane + 32 * it, imax = p2 ? 251 : 223;
                uint4 v[4];
#pragma unroll 1
                for (int n = 0;; n++) {
                    uint32_t bad = 0;
#pragma unroll
                    for (int k = 0; k < 4; k++) {
                        const int i = min(i0 + 64 * k, imax);
                        v[k] = ld_relaxed4(modp + (i < 224 ? (p2 ? 336 : 0) + i : (i < 238 ? 14 * j + i : 14 * j + i + 322)));
                        bad |= (v[k].x ^ tag) | (v[k].y ^ tag) | (v[k].z ^ tag) | (v[k].w ^ tag);
                    }
                    if (!__any_sync(~0u, bad & 0xFFFFu)) break;
                    if (n > SPIN_LIMIT) __trap();
                }
#pragma unroll
                for (int k = 0; k < 4; k++) {
                    const int i = min(i0 + 64 * k, imax);
                    if (i < 224) {
                        const int isc = i >= 112, c4 = i - 112 * isc;
                        const float one = isc ? 1.f : 0.f;
                        const uint32_t a = sb + M_ST + (c4 >> 2) * 64 + (c4 & 1) * 32 + (c4 & 2) * 4 + (isc ? 0 : 4);
                        sts1(a, pack2(bf_hi(v[k].x) + one, bf_hi(v[k].y) + one));
                        sts1(a + 16, pack2(bf_hi(v[k].z) + one, bf_hi(v[k].w) + one));
                    } else {
                        sts4(sb + M_G + (i - 224) * 16, make_uint4(v[k].x & 0xFFFF0000u, v[k].y & 0xFFFF0000u, v[k].z & 0xFFFF0000u, v[k].w & 0xFFFF0000u));
                    }
                }
                warp_arrive(BAR(p2 ? B_MOD2 : B_MOD1));
            }
            if (warp == 9) {
#pragma unroll 1
                for (int kv = 0; kv < 2; kv++) {
                    mbar_wait(BAR(B_PUB + kv), 0);
                    if (lane >= 1 && lane <= 2 && r >= lane) wait_flag(g_flag + kv * 128 + b - 8 * lane, target);
                    __syncwarp();
                    fence_async_global();
                    const uint32_t dst = sb + OFF_Y + (kv ? Y_VR : Y_K);
                    expect_e(BAR(B_KRFULL + kv), r >= 2 ? 28672 : r == 1 ? 14336 : 0);
                    if (r >= 2) bulk_e(dst, g_kv + (size_t)((b - 16) * 2 + kv) * 3584, 14336, BAR(B_KRFULL + kv));
                    if (r >= 1) bulk_e(dst + 14336, g_kv + (size_t)((b - 8) * 2 + kv) * 3584, 14336, BAR(B_KRFULL + kv));
                }
            } else if (warp == 11) {
                mbar_wait(BAR(B_VRFULL), 0);
                l2_prefetch_e((const char*)p.wg + (size_t)b * 12544, 12544);
                l2_prefetch_e((const char*)p.wu + (size_t)b * 12544, 12544);
                l2_prefetch_e((const char*)p.wd + (size_t)b * 12544, 12544);
            }
        }
        if (warp == 8 || warp == 11) {
            const int sec = warp == 11;
            if (sec) ring_loader<1>(p, sb, r, j); else ring_loader<0>(p, sb, r, j);
            mbar_wait(BAR(B_DONE), 0);
        } else if (warp == 9) {
#pragma unroll
            for (int ev = 0; ev < 4; ev++) expect_e(BAR(B_GFULL + ev), ev < 2 ? HALF : HALF + 4096);
            mbar_wait(BAR(B_PUB + 2), 0);
            const uint32_t* fp = g_flag + (2 + (lane >> 3)) * 128 + 8 * r + (lane & 7);
            const uint32_t* src = g_ox + (size_t)2 * r * 14336;
            const float2* ssrc = g_st + 2 * r * 512;
#pragma unroll 1
            for (int n = 0, ev = 0; ev < 4; n++) {
                if (ev == 1) mbar_wait(BAR(B_PUB + 3), 0);
                uint32_t ok = __ballot_sync(~0u, (int)(ld_relaxed(fp) - target) >= 0) >> (8 * ev);
                while ((ok & 0xFFu) == 0xFFu) {
                    asm volatile("fence.acquire.gpu;" ::: "memory");
                    fence_async_global();
                    const uint32_t bar = BAR(B_GFULL + ev);
                    bulk_e(sb + (ev == 0 ? OFF_X : OFF_Y + (ev & 1) * HALF), src + (ev >> 1) * (34 * 14336) + (ev & 1) * 14336, HALF, bar);
                    if (ev >= 2) bulk_e(sb + OFF_X + X_STAT + (ev & 1) * 4096, ssrc + (ev & 1) * 512, 4096, bar);
                    if (ev) PROFH(4 + ev);
                    ev++; ok >>= 8;
                }
                if (n > SPIN_LIMIT) __trap();
            }
#pragma unroll 1
            for (int ps = 0; ps < 3; ps++) {
                mbar_wait(BAR(B_PUB + 6 + ps), 0);
                if (lane < 4) wait_flag(g_flag + (6 + ps) * 128 + 8 * r + 2 * lane + kh, target);
                warp_arrive(BAR(B_HRDY + ps));
                PROFH(9 + ps);
            }
        } else {
            if (lane == 0) {
#pragma unroll 1
                for (int k = 0; k < 9; k++) {
                    mbar_wait(BAR(B_PUB + k), 0);
                    fence_gpu();
                    st_relaxed(g_flag + k * 128 + b, target);
                    if (k >= 3 && k <= 5) PROFH1(k - 3);
                }
            }
        }
    }
}

typedef CUresult (*EncodeFn)(CUtensorMap*, CUtensorMapDataType, cuuint32_t, void*, const cuuint64_t*, const cuuint64_t*, const cuuint32_t*,
                             const cuuint32_t*, CUtensorMapInterleave, CUtensorMapSwizzle, CUtensorMapL2promotion, CUtensorMapFloatOOBfill);

static void make_map(EncodeFn fn, CUtensorMap* m, const void* ptr, uint64_t d0, uint64_t d1, uint64_t d2, uint64_t s1, uint64_t s2,
                     uint32_t b0, uint32_t b1, uint32_t b2, CUtensorMapSwizzle sw) {
    cuuint64_t dims[3] = {d0, d1, d2}, strides[2] = {s1, s2};
    cuuint32_t box[3] = {b0, b1, b2}, es[3] = {1, 1, 1};
    CUresult rc = fn(m, CU_TENSOR_MAP_DATA_TYPE_BFLOAT16, 3, (void*)ptr, dims, strides, box, es, CU_TENSOR_MAP_INTERLEAVE_NONE, sw,
                     CU_TENSOR_MAP_L2_PROMOTION_L2_128B, CU_TENSOR_MAP_FLOAT_OOB_FILL_NONE);
    (void)rc;
}

extern "C" void kernel_launch(void* const* d_in, const int* in_sizes, int n_in, void* d_out, int out_size) {
    (void)in_sizes; (void)n_in; (void)out_size;
    static EncodeFn fn = nullptr;
    if (!fn) {
        cudaDriverEntryPointQueryResult st;
        cudaGetDriverEntryPoint("cuTensorMapEncodeTiled", (void**)&fn, cudaEnableDefault, &st);
        cudaFuncSetAttribute(fused_block_kernel, cudaFuncAttributeMaxDynamicSharedMemorySize, SMEM_BYTES);
    }
    Params p;
    p.x = (const bf16*)d_in[0];
    const bf16* wqkv = (const bf16*)d_in[1];
    p.wqkv = wqkv;
    p.wop = (const bf16*)d_in[2];
    p.wg = (const bf16*)d_in[4];
    p.wu = (const bf16*)d_in[5];
    p.wd = (const bf16*)d_in[6];
    p.c = (const bf16*)d_in[7];
    p.wmod = (const bf16*)d_in[8];
    p.out = (bf16*)d_out;
    p.zero = 0;
    make_map(fn, &p.wm, p.wmod, 2688, 448, 1, 5376, 5376 * 448, 16, 224, 1, CU_TENSOR_MAP_SWIZZLE_NONE);
    make_map(fn, &p.xm, p.x, 448, 2048, 1, 896, 896 * 2048, 64, 128, 1, CU_TENSOR_MAP_SWIZZLE_128B);
    make_map(fn, &p.qkv, wqkv, 1344, 448, 1, 2688, 2688 * 448, 64, 224, 1, CU_TENSOR_MAP_SWIZZLE_128B);
    make_map(fn, &p.wo, p.wop, 448, 448, 1, 896, 896 * 448, 64, 224, 1, CU_TENSOR_MAP_SWIZZLE_128B);
    make_map(fn, &p.ga, p.wg, 64, 448, 28, 3584, 128, 64, 32, 2, CU_TENSOR_MAP_SWIZZLE_128B);
    make_map(fn, &p.ua, p.wu, 64, 448, 28, 3584, 128, 64, 32, 2, CU_TENSOR_MAP_SWIZZLE_128B);
    make_map(fn, &p.gb, p.wg, 64, 448, 28, 3584, 128, 64, 64, 1, CU_TENSOR_MAP_SWIZZLE_128B);
    make_map(fn, &p.ub, p.wu, 64, 448, 28, 3584, 128, 64, 64, 1, CU_TENSOR_MAP_SWIZZLE_128B);
    make_map(fn, &p.gc, p.wg, 32, 448, 56, 3584, 64, 32, 64, 1, CU_TENSOR_MAP_SWIZZLE_64B);
    make_map(fn, &p.uc, p.wu, 32, 448, 56, 3584, 64, 32, 64, 1, CU_TENSOR_MAP_SWIZZLE_64B);
    make_map(fn, &p.dn, p.wd, 448, 1792, 1, 896, 896 * 1792, 64, 32, 1, CU_TENSOR_MAP_SWIZZLE_128B);
    fused_block_kernel<<<GRID, 384, SMEM_BYTES>>>(p);
}
```

```cpp
#include <cuda_runtime.h>
#include <cuda_bf16.h>
#include <cuda.h>
#include <stdint.h>

typedef __nv_bfloat16 bf16;

template<int TB> __device__ __forceinline__ void wgmma_rs_56(float* d, uint32_t a0, uint32_t a1, uint32_t a2, uint32_t a3, uint64_t db, int sd) {
  asm volatile("{\n.reg .pred p;\nsetp.ne.b32 p, %33, 0;\n"
    "wgmma.mma_async.sync.aligned.m64n56k16.f32.bf16.bf16 {%0,%1,%2,%3,%4,%5,%6,%7,%8,%9,%10,%11,%12,%13,%14,%15,%16,%17,%18,%19,%20,%21,%22,%23,%24,%25,%26,%27}, {%28,%29,%30,%31}, %32, p, 1, 1, %34;\n}\n"
    : "+f"(d[0]),"+f"(d[1]),"+f"(d[2]),"+f"(d[3]),"+f"(d[4]),"+f"(d[5]),"+f"(d[6]),"+f"(d[7]),"+f"(d[8]),"+f"(d[9]),"+f"(d[10]),"+f"(d[11]),"+f"(d[12]),"+f"(d[13]),"+f"(d[14]),"+f"(d[15]),"+f"(d[16]),"+f"(d[17]),"+f"(d[18]),"+f"(d[19]),"+f"(d[20]),"+f"(d[21]),"+f"(d[22]),"+f"(d[23]),"+f"(d[24]),"+f"(d[25]),"+f"(d[26]),"+f"(d[27])
    : "r"(a0), "r"(a1), "r"(a2), "r"(a3), "l"(db), "r"(sd), "n"(TB));
}
template<int TB> __device__ __forceinline__ void wgmma_ss_56(float* d, uint64_t da, uint64_t db, int sd) {
  asm volatile("{\n.reg .pred p;\nsetp.ne.b32 p, %30, 0;\n"
    "wgmma.mma_async.sync.aligned.m64n56k16.f32.bf16.bf16 {%0,%1,%2,%3,%4,%5,%6,%7,%8,%9,%10,%11,%12,%13,%14,%15,%16,%17,%18,%19,%20,%21,%22,%23,%24,%25,%26,%27}, %28, %29, p, 1, 1, 0, %31;\n}\n"
    : "+f"(d[0]),"+f"(d[1]),"+f"(d[2]),"+f"(d[3]),"+f"(d[4]),"+f"(d[5]),"+f"(d[6]),"+f"(d[7]),"+f"(d[8]),"+f"(d[9]),"+f"(d[10]),"+f"(d[11]),"+f"(d[12]),"+f"(d[13]),"+f"(d[14]),"+f"(d[15]),"+f"(d[16]),"+f"(d[17]),"+f"(d[18]),"+f"(d[19]),"+f"(d[20]),"+f"(d[21]),"+f"(d[22]),"+f"(d[23]),"+f"(d[24]),"+f"(d[25]),"+f"(d[26]),"+f"(d[27])
    : "l"(da), "l"(db), "r"(sd), "n"(TB));
}
template<int TB> __device__ __forceinline__ void wgmma_rs_256(float* d, uint32_t a0, uint32_t a1, uint32_t a2, uint32_t a3, uint64_t db, int sd) {
  asm volatile("{\n.reg .pred p;\nsetp.ne.b32 p, %133, 0;\n"
    "wgmma.mma_async.sync.aligned.m64n256k16.f32.bf16.bf16 {%0,%1,%2,%3,%4,%5,%6,%7,%8,%9,%10,%11,%12,%13,%14,%15,%16,%17,%18,%19,%20,%21,%22,%23,%24,%25,%26,%27,%28,%29,%30,%31,%32,%33,%34,%35,%36,%37,%38,%39,%40,%41,%42,%43,%44,%45,%46,%47,%48,%49,%50,%51,%52,%53,%54,%55,%56,%57,%58,%59,%60,%61,%62,%63,%64,%65,%66,%67,%68,%69,%70,%71,%72,%73,%74,%75,%76,%77,%78,%79,%80,%81,%82,%83,%84,%85,%86,%87,%88,%89,%90,%91,%92,%93,%94,%95,%96,%97,%98,%99,%100,%101,%102,%103,%104,%105,%106,%107,%108,%109,%110,%111,%112,%113,%114,%115,%116,%117,%118,%119,%120,%121,%122,%123,%124,%125,%126,%127}, {%128,%129,%130,%131}, %132, p, 1, 1, %134;\n}\n"
    : "+f"(d[0]),"+f"(d[1]),"+f"(d[2]),"+f"(d[3]),"+f"(d[4]),"+f"(d[5]),"+f"(d[6]),"+f"(d[7]),"+f"(d[8]),"+f"(d[9]),"+f"(d[10]),"+f"(d[11]),"+f"(d[12]),"+f"(d[13]),"+f"(d[14]),"+f"(d[15]),"+f"(d[16]),"+f"(d[17]),"+f"(d[18]),"+f"(d[19]),"+f"(d[20]),"+f"(d[21]),"+f"(d[22]),"+f"(d[23]),"+f"(d[24]),"+f"(d[25]),"+f"(d[26]),"+f"(d[27]),"+f"(d[28]),"+f"(d[29]),"+f"(d[30]),"+f"(d[31]),"+f"(d[32]),"+f"(d[33]),"+f"(d[34]),"+f"(d[35]),"+f"(d[36]),"+f"(d[37]),"+f"(d[38]),"+f"(d[39]),"+f"(d[40]),"+f"(d[41]),"+f"(d[42]),"+f"(d[43]),"+f"(d[44]),"+f"(d[45]),"+f"(d[46]),"+f"(d[47]),"+f"(d[48]),"+f"(d[49]),"+f"(d[50]),"+f"(d[51]),"+f"(d[52]),"+f"(d[53]),"+f"(d[54]),"+f"(d[55]),"+f"(d[56]),"+f"(d[57]),"+f"(d[58]),"+f"(d[59]),"+f"(d[60]),"+f"(d[61]),"+f"(d[62]),"+f"(d[63]),"+f"(d[64]),"+f"(d[65]),"+f"(d[66]),"+f"(d[67]),"+f"(d[68]),"+f"(d[69]),"+f"(d[70]),"+f"(d[71]),"+f"(d[72]),"+f"(d[73]),"+f"(d[74]),"+f"(d[75]),"+f"(d[76]),"+f"(d[77]),"+f"(d[78]),"+f"(d[79]),"+f"(d[80]),"+f"(d[81]),"+f"(d[82]),"+f"(d[83]),"+f"(d[84]),"+f"(d[85]),"+f"(d[86]),"+f"(d[87]),"+f"(d[88]),"+f"(d[89]),"+f"(d[90]),"+f"(d[91]),"+f"(d[92]),"+f"(d[93]),"+f"(d[94]),"+f"(d[95]),"+f"(d[96]),"+f"(d[97]),"+f"(d[98]),"+f"(d[99]),"+f"(d[100]),"+f"(d[101]),"+f"(d[102]),"+f"(d[103]),"+f"(d[104]),"+f"(d[105]),"+f"(d[106]),"+f"(d[107]),"+f"(d[108]),"+f"(d[109]),"+f"(d[110]),"+f"(d[111]),"+f"(d[112]),"+f"(d[113]),"+f"(d[114]),"+f"(d[115]),"+f"(d[116]),"+f"(d[117]),"+f"(d[118]),"+f"(d[119]),"+f"(d[120]),"+f"(d[121]),"+f"(d[122]),"+f"(d[123]),"+f"(d[124]),"+f"(d[125]),"+f"(d[126]),"+f"(d[127])
    : "r"(a0), "r"(a1), "r"(a2), "r"(a3), "l"(db), "r"(sd), "n"(TB));
}
template<int TB> __device__ __forceinline__ void wgmma_ss_128(float* d, uint64_t da, uint64_t db, int sd) {
  asm volatile("{\n.reg .pred p;\nsetp.ne.b32 p, %66, 0;\n"
    "wgmma.mma_async.sync.aligned.m64n128k16.f32.bf16.bf16 {%0,%1,%2,%3,%4,%5,%6,%7,%8,%9,%10,%11,%12,%13,%14,%15,%16,%17,%18,%19,%20,%21,%22,%23,%24,%25,%26,%27,%28,%29,%30,%31,%32,%33,%34,%35,%36,%37,%38,%39,%40,%41,%42,%43,%44,%45,%46,%47,%48,%49,%50,%51,%52,%53,%54,%55,%56,%57,%58,%59,%60,%61,%62,%63}, %64, %65, p, 1, 1, 0, %67;\n}\n"
    : "+f"(d[0]),"+f"(d[1]),"+f"(d[2]),"+f"(d[3]),"+f"(d[4]),"+f"(d[5]),"+f"(d[6]),"+f"(d[7]),"+f"(d[8]),"+f"(d[9]),"+f"(d[10]),"+f"(d[11]),"+f"(d[12]),"+f"(d[13]),"+f"(d[14]),"+f"(d[15]),"+f"(d[16]),"+f"(d[17]),"+f"(d[18]),"+f"(d[19]),"+f"(d[20]),"+f"(d[21]),"+f"(d[22]),"+f"(d[23]),"+f"(d[24]),"+f"(d[25]),"+f"(d[26]),"+f"(d[27]),"+f"(d[28]),"+f"(d[29]),"+f"(d[30]),"+f"(d[31]),"+f"(d[32]),"+f"(d[33]),"+f"(d[34]),"+f"(d[35]),"+f"(d[36]),"+f"(d[37]),"+f"(d[38]),"+f"(d[39]),"+f"(d[40]),"+f"(d[41]),"+f"(d[42]),"+f"(d[43]),"+f"(d[44]),"+f"(d[45]),"+f"(d[46]),"+f"(d[47]),"+f"(d[48]),"+f"(d[49]),"+f"(d[50]),"+f"(d[51]),"+f"(d[52]),"+f"(d[53]),"+f"(d[54]),"+f"(d[55]),"+f"(d[56]),"+f"(d[57]),"+f"(d[58]),"+f"(d[59]),"+f"(d[60]),"+f"(d[61]),"+f"(d[62]),"+f"(d[63])
    : "l"(da), "l"(db), "r"(sd), "n"(TB));
}
template<int TB> __device__ __forceinline__ void wgmma_ss_64(float* d, uint64_t da, uint64_t db, int sd) {
  asm volatile("{\n.reg .pred p;\nsetp.ne.b32 p, %34, 0;\n"
    "wgmma.mma_async.sync.aligned.m64n64k16.f32.bf16.bf16 {%0,%1,%2,%3,%4,%5,%6,%7,%8,%9,%10,%11,%12,%13,%14,%15,%16,%17,%18,%19,%20,%21,%22,%23,%24,%25,%26,%27,%28,%29,%30,%31}, %32, %33, p, 1, 1, 0, %35;\n}\n"
    : "+f"(d[0]),"+f"(d[1]),"+f"(d[2]),"+f"(d[3]),"+f"(d[4]),"+f"(d[5]),"+f"(d[6]),"+f"(d[7]),"+f"(d[8]),"+f"(d[9]),"+f"(d[10]),"+f"(d[11]),"+f"(d[12]),"+f"(d[13]),"+f"(d[14]),"+f"(d[15]),"+f"(d[16]),"+f"(d[17]),"+f"(d[18]),"+f"(d[19]),"+f"(d[20]),"+f"(d[21]),"+f"(d[22]),"+f"(d[23]),"+f"(d[24]),"+f"(d[25]),"+f"(d[26]),"+f"(d[27]),"+f"(d[28]),"+f"(d[29]),"+f"(d[30]),"+f"(d[31])
    : "l"(da), "l"(db), "r"(sd), "n"(TB));
}
template<int TB> __device__ __forceinline__ void wgmma_ss_112(float* d, uint64_t da, uint64_t db, int sd) {
  asm volatile("{\n.reg .pred p;\nsetp.ne.b32 p, %58, 0;\n"
    "wgmma.mma_async.sync.aligned.m64n112k16.f32.bf16.bf16 {%0,%1,%2,%3,%4,%5,%6,%7,%8,%9,%10,%11,%12,%13,%14,%15,%16,%17,%18,%19,%20,%21,%22,%23,%24,%25,%26,%27,%28,%29,%30,%31,%32,%33,%34,%35,%36,%37,%38,%39,%40,%41,%42,%43,%44,%45,%46,%47,%48,%49,%50,%51,%52,%53,%54,%55}, %56, %57, p, 1, 1, 0, %59;\n}\n"
    : "+f"(d[0]),"+f"(d[1]),"+f"(d[2]),"+f"(d[3]),"+f"(d[4]),"+f"(d[5]),"+f"(d[6]),"+f"(d[7]),"+f"(d[8]),"+f"(d[9]),"+f"(d[10]),"+f"(d[11]),"+f"(d[12]),"+f"(d[13]),"+f"(d[14]),"+f"(d[15]),"+f"(d[16]),"+f"(d[17]),"+f"(d[18]),"+f"(d[19]),"+f"(d[20]),"+f"(d[21]),"+f"(d[22]),"+f"(d[23]),"+f"(d[24]),"+f"(d[25]),"+f"(d[26]),"+f"(d[27]),"+f"(d[28]),"+f"(d[29]),"+f"(d[30]),"+f"(d[31]),"+f"(d[32]),"+f"(d[33]),"+f"(d[34]),"+f"(d[35]),"+f"(d[36]),"+f"(d[37]),"+f"(d[38]),"+f"(d[39]),"+f"(d[40]),"+f"(d[41]),"+f"(d[42]),"+f"(d[43]),"+f"(d[44]),"+f"(d[45]),"+f"(d[46]),"+f"(d[47]),"+f"(d[48]),"+f"(d[49]),"+f"(d[50]),"+f"(d[51]),"+f"(d[52]),"+f"(d[53]),"+f"(d[54]),"+f"(d[55])
    : "l"(da), "l"(db), "r"(sd), "n"(TB));
}
template<int TB> __device__ __forceinline__ void wgmma_rs_112(float* d, uint32_t a0, uint32_t a1, uint32_t a2, uint32_t a3, uint64_t db, int sd) {
  asm volatile("{\n.reg .pred p;\nsetp.ne.b32 p, %61, 0;\n"
    "wgmma.mma_async.sync.aligned.m64n112k16.f32.bf16.bf16 {%0,%1,%2,%3,%4,%5,%6,%7,%8,%9,%10,%11,%12,%13,%14,%15,%16,%17,%18,%19,%20,%21,%22,%23,%24,%25,%26,%27,%28,%29,%30,%31,%32,%33,%34,%35,%36,%37,%38,%39,%40,%41,%42,%43,%44,%45,%46,%47,%48,%49,%50,%51,%52,%53,%54,%55}, {%56,%57,%58,%59}, %60, p, 1, 1, %62;\n}\n"
    : "+f"(d[0]),"+f"(d[1]),"+f"(d[2]),"+f"(d[3]),"+f"(d[4]),"+f"(d[5]),"+f"(d[6]),"+f"(d[7]),"+f"(d[8]),"+f"(d[9]),"+f"(d[10]),"+f"(d[11]),"+f"(d[12]),"+f"(d[13]),"+f"(d[14]),"+f"(d[15]),"+f"(d[16]),"+f"(d[17]),"+f"(d[18]),"+f"(d[19]),"+f"(d[20]),"+f"(d[21]),"+f"(d[22]),"+f"(d[23]),"+f"(d[24]),"+f"(d[25]),"+f"(d[26]),"+f"(d[27]),"+f"(d[28]),"+f"(d[29]),"+f"(d[30]),"+f"(d[31]),"+f"(d[32]),"+f"(d[33]),"+f"(d[34]),"+f"(d[35]),"+f"(d[36]),"+f"(d[37]),"+f"(d[38]),"+f"(d[39]),"+f"(d[40]),"+f"(d[41]),"+f"(d[42]),"+f"(d[43]),"+f"(d[44]),"+f"(d[45]),"+f"(d[46]),"+f"(d[47]),"+f"(d[48]),"+f"(d[49]),"+f"(d[50]),"+f"(d[51]),"+f"(d[52]),"+f"(d[53]),"+f"(d[54]),"+f"(d[55])
    : "r"(a0), "r"(a1), "r"(a2), "r"(a3), "l"(db), "r"(sd), "n"(TB));
}

constexpr int DM = 448;
constexpr int NCTA = 128;
#define MAPPING 1
#define GRID 132
#define PINGPONG 0
#define WIN 4
#define WIN_END 25
#define MAP_S 4
constexpr int SPIN_LIMIT = 1 << 22;

constexpr uint32_t OFF_X = 0, OFF_Y = 114688, OFF_MISC = 229376, SMEM_BYTES = 232448;
constexpr uint32_t Y_VR = 0, Y_K = 28672, Y_KOWN = 57344, Y_VOWN = 71680, Y_Q = 86016;
constexpr uint32_t HALF = 57344;
constexpr uint32_t M_BAR = OFF_MISC;
constexpr uint32_t M_ST = OFF_MISC + 512;
constexpr uint32_t M_G = OFF_MISC + 2304;
constexpr uint32_t M_EPOCH = OFF_MISC + 3040;
enum { B_XFULL = 0, B_FULLK = 7, B_FULLV = 8, B_FULLQ, B_KRFULL, B_VRFULL, B_WOFULL, B_XCH, B_FULL = 16, B_MOD1 = 28, B_MOD2, B_WMFULL,
       B_EMPTY = 32, B_XFREE = B_EMPTY + 12, B_GEMV, B_PEER,
       B_PUB = 47,
       B_WMFREE = 56, B_HRDY, B_GFULL = B_HRDY + 3, B_DONE = 31 };
constexpr uint32_t X_STAT = 49152;

__device__ uint32_t g_ticket;
__device__ __align__(128) uint32_t g_mod[8 * 6 * DM];
__device__ __align__(128) uint32_t g_flag[9 * 16 * 8];
__device__ __align__(128) uint32_t g_kv[17 * 8 * 2 * 3584];
__device__ __align__(128) uint32_t g_ox[2 * 34 * 14336];
#define g_o g_ox
#define g_x1 (g_ox + 34 * 14336)
__device__ __align__(128) float2 g_st[34 * 8 * 64];
__device__ __align__(128) uint32_t g_h2[17 * 224 * 512];
#define PROFH(id)
#define PROFH1(id)
#define PROFC(id)

struct alignas(64) Params {
    CUtensorMap wm, xm, qkv, wo, ga, ua, gb, ub, gc, uc, dn;
    const bf16 *x, *c, *wqkv, *wmod, *wg, *wu, *wd, *wop;
    bf16* out;
    uint32_t zero;
};

__device__ __forceinline__ void mbar_init(uint32_t bar, int cnt) { asm volatile("mbarrier.init.shared::cta.b64 [%0], %1;" ::"r"(bar), "r"(cnt) : "memory"); }
__device__ __forceinline__ void mbar_expect_tx(uint32_t bar, uint32_t bytes) { asm volatile("mbarrier.arrive.expect_tx.shared::cta.b64 _, [%0], %1;" ::"r"(bar), "r"(bytes) : "memory"); }
__device__ __forceinline__ void mbar_arrive(uint32_t bar) { asm volatile("mbarrier.arrive.shared::cta.b64 _, [%0];" ::"r"(bar) : "memory"); }
__device__ __forceinline__ void mbar_wait(uint32_t bar, uint32_t parity) {
    uint32_t ok; int n = 0;
    do {
        asm volatile("{\n.reg .pred p;\nmbarrier.try_wait.parity.shared::cta.b64 p, [%1], %2;\nselp.u32 %0, 1, 0, p;\n}" : "=r"(ok) : "r"(bar), "r"(parity) : "memory");
        if (++n > SPIN_LIMIT) __trap();
    } while (!ok);
}
__device__ __forceinline__ void mbar_wait_cluster(uint32_t bar, uint32_t parity) {
    uint32_t ok; int n = 0;
    do {
        asm volatile("{\n.reg .pred p;\nmbarrier.try_wait.parity.acquire.cluster.shared::cta.b64 p, [%1], %2;\nselp.u32 %0, 1, 0, p;\n}" : "=r"(ok) : "r"(bar), "r"(parity) : "memory");
        if (++n > SPIN_LIMIT) __trap();
    } while (!ok);
}
__device__ __forceinline__ void warp_arrive(uint32_t bar) {
    __syncwarp();
    asm volatile("{\n.reg .pred p;\nelect.sync _|p, 0xffffffff;\n@p mbarrier.arrive.shared::cta.b64 _, [%0];\n}" ::"r"(bar) : "memory");
}
__device__ __forceinline__ int opaque(int v) { return __shfl_sync(~0u, v, 0); }
__device__ __forceinline__ int fresh_tid() { int v; asm volatile("mov.u32 %0, %%tid.x;" : "=r"(v)); return v; }
__device__ __forceinline__ void bar_sync(int id, int n) { asm volatile("bar.sync %0, %1;" ::"r"(id), "r"(n) : "memory"); }
__device__ __forceinline__ void bar_arrive(int id, int n) { asm volatile("bar.arrive %0, %1;" ::"r"(id), "r"(n) : "memory"); }
__device__ __forceinline__ void fence_async_smem() { asm volatile("fence.proxy.async.shared::cta;" ::: "memory"); }
__device__ __forceinline__ void fence_async_global() { asm volatile("fence.proxy.async.global;" ::: "memory"); }
__device__ __forceinline__ void fence_gpu() { asm volatile("fence.release.gpu;" ::: "memory"); }
__device__ __forceinline__ void tma3(uint32_t dst, const CUtensorMap* m, int c0, int c1, int c2, uint32_t bar) {
    asm volatile("cp.async.bulk.tensor.3d.shared::cluster.global.mbarrier::complete_tx::bytes [%0], [%1, {%3, %4, %5}], [%2];"
                 ::"r"(dst), "l"(m), "r"(bar), "r"(c0), "r"(c1), "r"(c2) : "memory");
}
__device__ __forceinline__ void bulk_load(uint32_t dst, const void* src, uint32_t bytes, uint32_t bar) {
    asm volatile("cp.async.bulk.shared::cluster.global.mbarrier::complete_tx::bytes [%0], [%1], %2, [%3];" ::"r"(dst), "l"(src), "r"(bytes), "r"(bar) : "memory");
}
__device__ __forceinline__ void expect_e(uint32_t bar, uint32_t bytes) {
    asm volatile("{\n.reg .pred p;\nelect.sync _|p, 0xffffffff;\n@p mbarrier.arrive.expect_tx.shared::cta.b64 _, [%0], %1;\n}" ::"r"(bar), "r"(bytes) : "memory");
}
__device__ __forceinline__ void tma3_e(uint32_t dst, const CUtensorMap* m, int c0, int c1, int c2, uint32_t bar) {
    asm volatile("{\n.reg .pred p;\nelect.sync _|p, 0xffffffff;\n@p cp.async.bulk.tensor.3d.shared::cluster.global.mbarrier::complete_tx::bytes [%0], [%1, {%3, %4, %5}], [%2];\n}"
                 ::"r"(dst), "l"(m), "r"(bar), "r"(c0), "r"(c1), "r"(c2) : "memory");
}
__device__ __forceinline__ void bulk_e(uint32_t dst, const void* src, uint32_t bytes, uint32_t bar) {
    asm volatile("{\n.reg .pred p;\nelect.sync _|p, 0xffffffff;\n@p cp.async.bulk.shared::cluster.global.mbarrier::complete_tx::bytes [%0], [%1], %2, [%3];\n}"
                 ::"r"(dst), "l"(src), "r"(bytes), "r"(bar) : "memory");
}
__device__ __forceinline__ void init_e(uint32_t bar, int cnt) {
    asm volatile("{\n.reg .pred p;\nelect.sync _|p, 0xffffffff;\n@p mbarrier.init.shared::cta.b64 [%0], %1;\n}" ::"r"(bar), "r"(cnt) : "memory");
}
__device__ __forceinline__ void l2_prefetch_e(const void* src, uint32_t bytes) {
    asm volatile("{\n.reg .pred p;\nelect.sync _|p, 0xffffffff;\n@p cp.async.bulk.prefetch.L2.global [%0], %1;\n}" ::"l"(src), "r"(bytes) : "memory");
}
__device__ __forceinline__ uint32_t ld_relaxed(const uint32_t* p) { uint32_t v; asm volatile("ld.relaxed.gpu.global.u32 %0, [%1];" : "=r"(v) : "l"(p) : "memory"); return v; }
__device__ __forceinline__ void st_relaxed(uint32_t* p, uint32_t v) { asm volatile("st.relaxed.gpu.global.u32 [%0], %1;" ::"l"(p), "r"(v) : "memory"); }
__device__ __forceinline__ uint4 ld_relaxed4(const uint4* p) { uint4 v; asm volatile("ld.relaxed.gpu.global.v4.u32 {%0,%1,%2,%3}, [%4];" : "=r"(v.x), "=r"(v.y), "=r"(v.z), "=r"(v.w) : "l"(p) : "memory"); return v; }
__device__ __forceinline__ void st_relaxed4(uint4* p, uint4 v) { asm volatile("st.relaxed.gpu.global.v4.u32 [%0], {%1,%2,%3,%4};" ::"l"(p), "r"(v.x), "r"(v.y), "r"(v.z), "r"(v.w) : "memory"); }
__device__ __forceinline__ uint4 ldg_nc4(const void* p) { uint4 v; asm volatile("ld.global.nc.L1::no_allocate.v4.u32 {%0,%1,%2,%3}, [%4];" : "=r"(v.x), "=r"(v.y), "=r"(v.z), "=r"(v.w) : "l"(p)); return v; }
__device__ __forceinline__ uint32_t ldg_nc(const void* p) { uint32_t v; asm volatile("ld.global.nc.u32 %0, [%1];" : "=r"(v) : "l"(p)); return v; }
__device__ __forceinline__ uint32_t ld_acquire(const uint32_t* p) { uint32_t v; asm volatile("ld.acquire.gpu.global.u32 %0, [%1];" : "=r"(v) : "l"(p) : "memory"); return v; }
__device__ __forceinline__ uint4 lds4(uint32_t a) { uint4 v; asm volatile("ld.shared.v4.u32 {%0,%1,%2,%3}, [%4];" : "=r"(v.x), "=r"(v.y), "=r"(v.z), "=r"(v.w) : "r"(a) : "memory"); return v; }
__device__ __forceinline__ float2 lds2f(uint32_t a) { float2 v; asm volatile("ld.shared.v2.f32 {%0,%1}, [%2];" : "=f"(v.x), "=f"(v.y) : "r"(a) : "memory"); return v; }
__device__ __forceinline__ uint32_t lds1(uint32_t a) { uint32_t v; asm volatile("ld.shared.u32 %0, [%1];" : "=r"(v) : "r"(a) : "memory"); return v; }
__device__ __forceinline__ void sts4(uint32_t a, uint4 v) { asm volatile("st.shared.v4.u32 [%0], {%1,%2,%3,%4};" ::"r"(a), "r"(v.x), "r"(v.y), "r"(v.z), "r"(v.w) : "memory"); }
__device__ __forceinline__ void sts2(uint32_t a, uint32_t x, uint32_t y) { asm volatile("st.shared.v2.u32 [%0], {%1,%2};" ::"r"(a), "r"(x), "r"(y) : "memory"); }
__device__ __forceinline__ void sts1(uint32_t a, uint32_t v) { asm volatile("st.shared.u32 [%0], %1;" ::"r"(a), "r"(v) : "memory"); }
__device__ __forceinline__ void stsm4(uint32_t a, uint32_t r0, uint32_t r1, uint32_t r2, uint32_t r3) {
    asm volatile("stmatrix.sync.aligned.m8n8.x4.shared.b16 [%0], {%1,%2,%3,%4};" ::"r"(a), "r"(r0), "r"(r1), "r"(r2), "r"(r3));
}
__device__ __forceinline__ uint32_t pack2(float lo, float hi) { uint32_t r; asm("cvt.rn.bf16x2.f32 %0, %1, %2;" : "=r"(r) : "f"(hi), "f"(lo)); return r; }
__device__ __forceinline__ uint32_t pack2_relu(float lo, float hi) { uint32_t r; asm("cvt.rn.relu.bf16x2.f32 %0, %1, %2;" : "=r"(r) : "f"(hi), "f"(lo)); return r; }
__device__ __forceinline__ uint32_t hfma2(uint32_t a, uint32_t b, uint32_t c) { uint32_t r; asm("fma.rn.bf16x2 %0, %1, %2, %3;" : "=r"(r) : "r"(a), "r"(b), "r"(c)); return r; }
__device__ __forceinline__ uint32_t hmul2(uint32_t a, uint32_t b) { uint32_t r; asm("mul.rn.bf16x2 %0, %1, %2;" : "=r"(r) : "r"(a), "r"(b)); return r; }
__device__ __forceinline__ float bf_lo(uint32_t v) { return __uint_as_float(v << 16); }
__device__ __forceinline__ float bf_hi(uint32_t v) { return __uint_as_float(v & 0xFFFF0000u); }
__device__ __forceinline__ float bf_round(float v) { return bf_lo(pack2(v, 0.f)); }
__device__ __forceinline__ float ex2(float x) { float r; asm("ex2.approx.ftz.f32 %0, %1;" : "=f"(r) : "f"(x)); return r; }
__device__ __forceinline__ void mma16816(float* d, uint32_t a0, uint32_t a1, uint32_t a2, uint32_t a3, uint32_t b0, uint32_t b1) {
    asm("mma.sync.aligned.m16n8k16.row.col.f32.bf16.bf16.f32 {%0,%1,%2,%3}, {%4,%5,%6,%7}, {%8,%9}, {%0,%1,%2,%3};"
        : "+f"(d[0]), "+f"(d[1]), "+f"(d[2]), "+f"(d[3]) : "r"(a0), "r"(a1), "r"(a2), "r"(a3), "r"(b0), "r"(b1));
}
__device__ __forceinline__ void mma16816_first(float* d, uint32_t a0, uint32_t a1, uint32_t a2, uint32_t a3, uint32_t b0, uint32_t b1) {
    asm volatile("mma.sync.aligned.m16n8k16.row.col.f32.bf16.bf16.f32 {%0,%1,%2,%3}, {%4,%5,%6,%7}, {%8,%9}, {%10,%10,%10,%10};"
        : "=f"(d[0]), "=f"(d[1]), "=f"(d[2]), "=f"(d[3]) : "r"(a0), "r"(a1), "r"(a2), "r"(a3), "r"(b0), "r"(b1), "f"(0.f));
}
__device__ __forceinline__ void mma16816_v(float* d, uint32_t a0, uint32_t a1, uint32_t a2, uint32_t a3, uint32_t b0, uint32_t b1) {
    asm volatile("mma.sync.aligned.m16n8k16.row.col.f32.bf16.bf16.f32 {%0,%1,%2,%3}, {%4,%5,%6,%7}, {%8,%9}, {%0,%1,%2,%3};"
        : "+f"(d[0]), "+f"(d[1]), "+f"(d[2]), "+f"(d[3]) : "r"(a0), "r"(a1), "r"(a2), "r"(a3), "r"(b0), "r"(b1));
}
__device__ __forceinline__ void mma1688(float* d, uint32_t a0, uint32_t a1, uint32_t b0) {
    asm("mma.sync.aligned.m16n8k8.row.col.f32.bf16.bf16.f32 {%0,%1,%2,%3}, {%4,%5}, {%6}, {%0,%1,%2,%3};"
        : "+f"(d[0]), "+f"(d[1]), "+f"(d[2]), "+f"(d[3]) : "r"(a0), "r"(a1), "r"(b0));
}
__device__ __forceinline__ void ldsm4(uint32_t a, uint32_t* r) {
    asm volatile("ldmatrix.sync.aligned.m8n8.x4.shared.b16 {%0,%1,%2,%3}, [%4];" : "=r"(r[0]), "=r"(r[1]), "=r"(r[2]), "=r"(r[3]) : "r"(a));
}
__device__ __forceinline__ void ldsm4t(uint32_t a, uint32_t* r) {
    asm volatile("ldmatrix.sync.aligned.m8n8.x4.trans.shared.b16 {%0,%1,%2,%3}, [%4];" : "=r"(r[0]), "=r"(r[1]), "=r"(r[2]), "=r"(r[3]) : "r"(a));
}
__device__ __forceinline__ float rcp(float x) { float r; asm("rcp.approx.ftz.f32 %0, %1;" : "=f"(r) : "f"(x)); return r; }
__device__ __forceinline__ uint2 ld_relaxed2(const void* p) { uint2 v; asm volatile("ld.relaxed.gpu.global.v2.u32 {%0,%1}, [%2];" : "=r"(v.x), "=r"(v.y) : "l"(p) : "memory"); return v; }
__device__ __forceinline__ void st_relaxed2(void* p, uint32_t x, uint32_t y) { asm volatile("st.relaxed.gpu.global.v2.u32 [%0], {%1,%2};" ::"l"(p), "r"(max(x, 1u)), "r"(max(y, 1u)) : "memory"); }
__device__ __forceinline__ constexpr uint64_t dconst(uint32_t lbo, uint32_t sbo, uint32_t swz) {
    return ((uint64_t)(lbo >> 4) << 16) | ((uint64_t)(sbo >> 4) << 32) | ((uint64_t)swz << 62);
}
__device__ __forceinline__ uint64_t mkdesc(uint32_t addr, uint64_t c) { return c | (uint64_t)((addr & 0x3FFFF) >> 4); }
#define WG_FENCE() asm volatile("wgmma.fence.sync.aligned;" ::: "memory")
#define WG_COMMIT() asm volatile("wgmma.commit_group.sync.aligned;" ::: "memory")
#define WG_WAIT(n) asm volatile("wgmma.wait_group.sync.aligned %0;" ::"n"(n) : "memory")
template <int N> __device__ __forceinline__ void reg_fence(float* d) {
#pragma unroll
    for (int i = 0; i < N; i++) asm volatile("" : "+f"(d[i])::"memory");
}
template <int N> __device__ __forceinline__ void reg_def(float* d) {
#pragma unroll
    for (int i = 0; i < N; i++) asm volatile("" : "=f"(d[i]));
}
template <int N> __device__ __forceinline__ void reg_def(uint32_t* d) {
#pragma unroll
    for (int i = 0; i < N; i++) asm volatile("" : "=r"(d[i]));
}
__device__ __forceinline__ bool is_unset(uint4 v) { return min(min(v.x, v.y), min(v.z, v.w)) == 0u; }
__device__ __forceinline__ uint4 nz4(uint32_t a, uint32_t b, uint32_t c, uint32_t d) { return make_uint4(max(a, 1u), max(b, 1u), max(c, 1u), max(d, 1u)); }
__device__ __forceinline__ void wait_flag(const uint32_t* p, uint32_t target) {
    int n = 0;
    while ((int)(ld_relaxed(p) - target) < 0) { if (++n > SPIN_LIMIT) __trap(); }
    asm volatile("fence.acquire.gpu;" ::: "memory");
}
__device__ __forceinline__ float silu_bf(uint32_t cbits) {
    const float c = __uint_as_float(cbits << 16);
    return bf_round(__fdividef(c, 1.f + fminf(ex2(-1.4426950408889634f * c), 1e30f)));
}
__device__ __forceinline__ void gemv_part(uint32_t wmbuf, int npanel, int wp, int lane) {
    const uint32_t wa = wmbuf + wp * 512 + (8 * (lane >> 4) + (lane & 7)) * 32 + ((lane >> 3) & 1) * 16;
    uint2 B[4];
#pragma unroll
    for (int i = 0; i < 4; i++) { const float2 v = lds2f(wmbuf + 28672 + (wp + 8 * i) * 32 + (lane & 3) * 8); B[i] = make_uint2(__float_as_uint(v.x), __float_as_uint(v.y)); }
#pragma unroll 1
    for (int pn = 0; pn < npanel; pn++) {
        float d[4] = {};
        uint32_t A[16];
#pragma unroll
        for (int i = 0; i < 4; i++) ldsm4t(wa + pn * 14336 + (i < 3 || wp < 4 ? i : 0) * 4096, A + 4 * i);
#pragma unroll
        for (int i = 0; i < 4; i++) mma16816(d, A[4 * i], A[4 * i + 1], A[4 * i + 2], A[4 * i + 3], B[i].x, B[i].y);
        if ((lane & 3) == 0) {
            sts1(wmbuf + 29696 + (wp * 32 + pn * 16 + (lane >> 2)) * 4, __float_as_uint(d[0]));
            sts1(wmbuf + 29696 + (wp * 32 + pn * 16 + 8 + (lane >> 2)) * 4, __float_as_uint(d[2]));
        }
    }
}
__device__ __forceinline__ int pass_f(int fs, int ps) { return 224 * fs + ((fs & 1) ? (ps == 0 ? 96 : ps == 1 ? 32 : 0) : (ps == 0 ? 0 : ps == 1 ? 128 : 192)); }
__device__ __forceinline__ constexpr uint32_t slot_off(int l) { return (l < 3 || l > 6 ? l : l == 6 ? 3 : l + 1) * 16384; }
__device__ __forceinline__ void ln_coeffs(float mean, float msq, uint32_t& r2, uint32_t& n2) {
    const float rs = bf_round(rsqrtf(fmaxf(msq - mean * mean, 0.f) + 1e-5f));
    r2 = pack2(rs, rs);
    n2 = pack2(-mean * rs, -mean * rs);
}

template <int sec> __device__ __forceinline__ void ring_loader(const Params& p, uint32_t sb_, int r_, int j_) {
    const uint32_t sb = opaque(sb_);
    const int r = opaque(r_), j = opaque(j_), nq = j >> 1, fs = 4 * (j & 1) + nq;
    const int fa = pass_f(fs, 0), fb = pass_f(fs, 1), fc = pass_f(fs, 2);
#define BAR(i) (sb + M_BAR + 8 * (i))
#define kh (j & 1)
            int sl = 0;
#pragma unroll 1
            for (int s = 0; s < 28; s++) {
                if (s >= 1 && s < 6) mbar_wait(BAR(B_FULL + s - 1), 0);
                const int ps = s < 14 ? 0 : s < 21 ? 1 : 2;
                const uint32_t half = ps < 2 ? 8192 : 4096;
                mbar_wait(BAR(B_EMPTY + sl), (s >= 7 && s < 14) || s >= 21);
                expect_e(BAR(B_FULL + sl), half);
                tma3_e(sb + slot_off(sl) + sec * half, &p.ga + 2 * ps + sec, 0, ps ? 64 * sl : 32 * s, ps == 0 ? fa >> 6 : ps == 1 ? fb >> 6 : fc >> 5, BAR(B_FULL + sl));
                sl = sl == 6 ? 0 : sl + 1;
            }
            if (!sec) PROFH(3);
#pragma unroll 1
            for (int e = 0; e < 4; e++) {
                const uint32_t dst = sb + slot_off(e) + sec * 8192, bar = BAR(B_FULL + e);
                const int f = (e < 2 ? fa + 64 * e : e == 2 ? fb : fc) + 32 * sec;
                mbar_wait(BAR(B_EMPTY + e), 0);
                expect_e(bar, e == 3 && sec ? 0 : 8192);
                if (!(e == 3 && sec)) { tma3_e(dst, &p.dn, 112 * nq + 48, f, 0, bar); tma3_e(dst + 4096, &p.dn, 112 * nq, f, 0, bar); }
            }
            sl = 4;
            int e = 4;
#pragma unroll 1
            for (int grp = 0; grp < 9; grp++) {
                const int ps = grp >= 6 ? 2 : grp >= 3 ? 1 : 0;
                int sidx = grp - 3 * ps;
                if (sec && sidx == 0) { mbar_wait(BAR(B_HRDY + ps), 0); fence_async_global(); }
                sidx += sidx >= nq;
                int f = pass_f(4 * kh + sidx, ps);
#pragma unroll 1
                for (int k = 4 >> ps; k > 0; k--, e++, f += 32) {
                    const uint32_t dst = sb + slot_off(sl), bar = BAR(B_FULL + sl);
                    mbar_wait(BAR(B_EMPTY + sl), e >= 12 && e < 24);
                    if (e < WIN_END) mbar_wait(BAR(B_FULL + (sl >= WIN ? sl - WIN : sl + 12 - WIN)), e - WIN >= 12);
                    expect_e(bar, 8192);
                    if (!sec) { tma3_e(dst, &p.dn, 112 * nq + 48, f, 0, bar); tma3_e(dst + 4096, &p.dn, 112 * nq, f, 0, bar); }
                    else bulk_e(dst + 8192, g_h2 + (size_t)r * (224 * 512) + f * 64, 8192, bar);
                    sl = sl == 11 ? 0 : sl + 1;
                }
            }
            if (!sec) PROFH(4);
}

__global__ void __cluster_dims__(2, 1, 1) __launch_bounds__(384, 1) fused_block_kernel(const __grid_constant__ Params p) {
    extern __shared__ __align__(1024) unsigned char smem[];
    const uint32_t sb = (uint32_t)__cvta_generic_to_shared(smem);
    const int tid = threadIdx.x, lane = tid & 31, warp = __shfl_sync(~0u, tid >> 5, 0);
    const int m = blockIdx.x >> 1;
    int r, nq;
    {
        int g, i;
        if (m < MAP_S) { g = m < 4 ? 15 : 16; i = m & 3; }
        else if (m < MAP_S + 32) { g = (m - MAP_S) & 7; i = (m - MAP_S) >> 3; }
        else if (m < MAP_S + 60) { i = (m - MAP_S - 32) / 7; g = 8 + (m - MAP_S - 32) - 7 * i; }
        else { g = 16; i = m & 3; }
        r = g; nq = i;
    }
    const int j = opaque(2 * nq + (blockIdx.x & 1)), b = 8 * r + j, fs = 4 * kh + nq;
    const uint32_t sc = r == 16;
    if (lane == 0 && warp < 9 && warp != 6 && warp != 7) {
        const int i0 = warp == 8 ? 0 : 8 + 8 * warp, cnt = warp == 0 || warp == 8 ? 1 : warp < 3 ? 2 : 8;
#pragma unroll
        for (int k = 0; k < 8; k++) if (i0 + k != B_WMFULL) mbar_init(BAR(i0 + k), cnt);
        asm volatile("fence.mbarrier_init.release.cluster;" ::: "memory");
        fence_async_smem();
    }

    if (warp < 8) {
        const int w = warp >> 2, wi = warp & 3;
#define COORDS const int t = fresh_tid() & 127, lane = t & 31, q = lane & 3, lr = lane >> 2, ra = 64 * w + 16 * wi + lr; \
        const uint32_t lx = (lane >> 4) ^ (lane & 7), mrow = (64 * w + 16 * wi + ((lane >> 3) & 1) * 8 + (lane & 7)) * 128; \
        (void)q; (void)lr; (void)ra; (void)lx; (void)mrow;
        const int sid = 2 * (j & 3) + w;
#define RUN(k) (!sc || sid == (k))
#define WAIT(i, par) mbar_wait(BAR(i), (par) | sc)
        constexpr uint64_t DB128 = dconst(4096, 1024, 1);
        bar_arrive(9, 384);
        bar_sync(0, 384);
        asm volatile("barrier.cluster.arrive.relaxed.aligned;" ::: "memory");
        asm volatile("setmaxnreg.inc.sync.aligned.u32 224;");
        PROFC(0);
        uint32_t xr[16];
        {
            COORDS
            uint32_t h[112];
            if (RUN(0)) {
                float ds[4] = {}, da[2][4] = {}, db[2][4] = {};
                const uint32_t ONE2 = 0x3F803F80u;
                if (kh == 0) { WAIT(B_WMFULL, 0); gemv_part(sb + OFF_Y + HALF, 1, warp, lane); warp_arrive(BAR(B_GEMV)); }
#pragma unroll
                for (int kb = 0; kb < 7; kb++) {
                    WAIT(B_XFULL + kb, 0);
#pragma unroll
                    for (int k4 = 0; k4 < 4; k4++) ldsm4(sb + OFF_X + mrow + kb * 16384 + (((2 * k4) ^ lx) << 4), h + 16 * kb + 4 * k4);
#pragma unroll
                    for (int k4 = 0; k4 < 4; k4++) {
                        const uint32_t* f = h + 16 * kb + 4 * k4;
                        mma16816(ds, f[0], f[1], f[2], f[3], ONE2, ONE2);
                        mma1688(da[0], f[0], f[1], f[0]); mma1688(db[0], f[0], f[1], f[1]);
                        mma1688(da[1], f[2], f[3], f[2]); mma1688(db[1], f[2], f[3], f[3]);
                    }
                }
#pragma unroll
                for (int i = 0; i < 4; i++) {
                    const int ch = 7 * j + 2 * i + (lane >> 4);
                    ldsm4(sb + OFF_X + mrow + (ch >> 3) * 16384 + (((ch ^ lane) & 7) << 4), xr + 4 * i);
                }
                warp_arrive(BAR(B_XFREE));
                float qa = (lr & 1) ? da[0][1] + da[1][1] : da[0][0] + da[1][0];
                float qb = (lr & 1) ? db[0][3] + db[1][3] : db[0][2] + db[1][2];
                const int src = (lane & ~3) | (lr >> 1);
                qa = __shfl_sync(~0u, qa, src);
                qb = __shfl_sync(~0u, qb, src);
                uint32_t ra2, na2, rb2, nb2;
                ln_coeffs(ds[0] * (1.f / DM), qa * (1.f / DM), ra2, na2);
                ln_coeffs(ds[2] * (1.f / DM), qb * (1.f / DM), rb2, nb2);
#pragma unroll
                for (int i = 0; i < 112; i += 2) { h[i] = hfma2(h[i], ra2, na2); h[i + 1] = hfma2(h[i + 1], rb2, nb2); }
                if (kh == 1) { WAIT(B_WMFULL, 0); gemv_part(sb + OFF_Y + HALF, 2, warp, lane); warp_arrive(BAR(B_GEMV)); }
            } else { reg_def<112>(h); reg_def<16>(xr); }
            PROFC(1);
            if (RUN(1)) {
                float ak[28], av[28], aq[28];
                uint32_t kp[14], vp[14];
                const uint64_t bk0 = mkdesc(sb + OFF_Y, DB128) + kh, bv0 = mkdesc(sb + OFF_Y + HALF, DB128) + kh, bq0 = mkdesc(sb + OFF_X, DB128) + kh;
                uint32_t* kvg = g_kv + (size_t)(b * 2) * 3584 + (8 * w + 2 * wi) * 224 + lane;
                WAIT(B_FULLK, 0);
                WAIT(B_MOD1, 0);
                PROFC(2);
                reg_def<28>(ak);
#pragma unroll
                for (int g4 = 0; g4 < 4; g4++) {
#pragma unroll
                    for (int ks = 7 * g4; ks < 7 * g4 + 7; ks++) {
                        const uint4 st = *(const uint4*)(smem + M_ST + ks * 64 + q * 16);
                        h[4 * ks] = hfma2(h[4 * ks], st.x, st.y); h[4 * ks + 1] = hfma2(h[4 * ks + 1], st.x, st.y);
                        h[4 * ks + 2] = hfma2(h[4 * ks + 2], st.z, st.w); h[4 * ks + 3] = hfma2(h[4 * ks + 3], st.z, st.w);
                    }
                    WG_FENCE();
#pragma unroll
                    for (int ks = 7 * g4; ks < 7 * g4 + 7; ks++) wgmma_rs_56<1>(ak, h[4 * ks], h[4 * ks + 1], h[4 * ks + 2], h[4 * ks + 3], bk0 + ks * 128, ks != 0);
                }
                WG_COMMIT();
                PROFC(3);
                WAIT(B_FULLV, 0);
                reg_def<28>(av);
                WG_FENCE();
#pragma unroll
                for (int ks = 0; ks < 8; ks++) wgmma_rs_56<1>(av, h[4 * ks], h[4 * ks + 1], h[4 * ks + 2], h[4 * ks + 3], bv0 + ks * 128, ks != 0);
                WG_COMMIT();
                WG_WAIT(1);
                reg_fence<28>(ak);
#pragma unroll
                for (int g = 0; g < 7; g++) {
                    kp[2 * g] = pack2(ak[4 * g], ak[4 * g + 1]); kp[2 * g + 1] = pack2(ak[4 * g + 2], ak[4 * g + 3]);
                    kvg[g * 32] = kp[2 * g]; kvg[224 + g * 32] = kp[2 * g + 1];
                }
                warp_arrive(BAR(B_PUB));
                PROFC(4);
                WG_FENCE();
#pragma unroll
                for (int ks = 8; ks < 28; ks++) wgmma_rs_56<1>(av, h[4 * ks], h[4 * ks + 1], h[4 * ks + 2], h[4 * ks + 3], bv0 + ks * 128, 1);
                WG_COMMIT();
                WAIT(B_FULLQ, 0);
                reg_def<28>(aq);
                WG_FENCE();
#pragma unroll
                for (int ks = 0; ks < 8; ks++) wgmma_rs_56<1>(aq, h[4 * ks], h[4 * ks + 1], h[4 * ks + 2], h[4 * ks + 3], bq0 + ks * 128, ks != 0);
                WG_COMMIT();
                WG_WAIT(1);
                reg_fence<28>(av);
#pragma unroll
                for (int g = 0; g < 7; g++) {
                    vp[2 * g] = pack2(av[4 * g], av[4 * g + 1]); vp[2 * g + 1] = pack2(av[4 * g + 2], av[4 * g + 3]);
                    kvg[3584 + g * 32] = vp[2 * g]; kvg[3584 + 224 + g * 32] = vp[2 * g + 1];
                }
                warp_arrive(BAR(B_PUB + 1));
                PROFC(5);
                WG_FENCE();
#pragma unroll
                for (int ks = 8; ks < 28; ks++) wgmma_rs_56<1>(aq, h[4 * ks], h[4 * ks + 1], h[4 * ks + 2], h[4 * ks + 3], bq0 + ks * 128, 1);
                WG_COMMIT();
                WAIT(B_PUB + 1, 0);
                const uint32_t ko = sb + OFF_Y + Y_KOWN + (8 * w + 2 * wi) * 896 + lane * 4;
                const uint32_t qo = sb + OFF_Y + Y_Q + (8 * w + 2 * wi) * 1024 + lane * 4;
#pragma unroll
                for (int g = 0; g < 7; g++) {
                    sts1(ko + g * 128, kp[2 * g]); sts1(ko + 896 + g * 128, kp[2 * g + 1]);
                    sts1(ko + (Y_VOWN - Y_KOWN) + g * 128, vp[2 * g]); sts1(ko + (Y_VOWN - Y_KOWN) + 896 + g * 128, vp[2 * g + 1]);
                }
                WG_WAIT(0);
                reg_fence<28>(aq);
                __syncwarp();
                if (lane < 3 && w == 1) mbar_arrive(BAR(B_EMPTY + lane));
#pragma unroll
                for (int g = 0; g < 7; g++) {
                    const uint32_t q0 = pack2(aq[4 * g], aq[4 * g + 1]), q1 = pack2(aq[4 * g + 2], aq[4 * g + 3]);
                    if (g == 3) {
                        sts1(qo + 3 * 128, q < 2 ? q0 : 0u); sts1(qo + 1024 + 3 * 128, q < 2 ? q1 : 0u);
                        sts1(qo + 4 * 128, q < 2 ? 0u : q0); sts1(qo + 1024 + 4 * 128, q < 2 ? 0u : q1);
                    } else {
                        const int ch = g < 3 ? g : g + 1;
                        sts1(qo + ch * 128, q0); sts1(qo + 1024 + ch * 128, q1);
                    }
                }
                if (!sc) bar_sync(3, 256);
            }
        }
        PROFC(6);
        WAIT(B_KRFULL, 0);
        PROFC(7);
        if (RUN(2)) {
#pragma unroll 1
            for (int hf = sc; hf < 2; hf++) {
                COORDS
                float s[136];
                float na = 0.f, nb = 0.f;
                const float CS = 0.18898223650461361f * 1.4426950408889634f;
                const int kg0 = 8 * hf + 2 * wi;
                const int pmin = 16 - 8 * r - 4 * hf - wi;
                const float NEG = __int_as_float(0xFF800000);
                {
                    uint32_t F[8];
                    const uint32_t qa = sb + OFF_Y + Y_Q + (kg0 + ((lane >> 3) & 1)) * 1024 + (4 * w + (lane >> 4)) * 128 + (lane & 7) * 16;
                    ldsm4(qa, F); ldsm4(qa + 256, F + 4);
                    uint32_t ka = sb + OFF_Y + Y_K + kg0 * 896 + (3 * w + (lane >> 3)) * 128 + (lane & 7) * 16;
#pragma unroll
                    for (int g = 0; g < 34; g++) {
                        uint32_t B[4];
                        if (g >= 12 && g % 4 == 0) ka += __float_as_uint(s[4 * (g - 12)]) & p.zero;
                        ldsm4(ka + g * 896, B);
                        mma16816_first(s + 4 * g, F[0], F[1], F[2], F[3], B[0], B[1]);
                        mma16816_v(s + 4 * g, F[4], F[5], F[6], F[7], B[2], B[3]);
                    }
                    const bool c0 = 2 * q > lr, c1 = 2 * q + 1 > lr;
                    if (!c0) { s[0] = NEG; s[6] = NEG; }
                    if (!c1) { s[1] = NEG; s[7] = NEG; }
                    s[2] = NEG; s[3] = NEG;
                    if (c0) { s[128] = NEG; s[134] = NEG; }
                    if (c1) { s[129] = NEG; s[135] = NEG; }
                    s[132] = NEG; s[133] = NEG;
                    float ma = NEG, mb = NEG;
#pragma unroll
                    for (int pp = 0; pp < 17; pp++) {
                        const float* e = s + 8 * pp;
                        const float bias = pp < pmin ? NEG : 0.f;
                        ma = fmaxf(ma, fmaxf(fmaxf(e[0], e[1]), fmaxf(e[4], e[5])) + bias);
                        mb = fmaxf(mb, fmaxf(fmaxf(e[2], e[3]), fmaxf(e[6], e[7])) + bias);
                    }
                    ma = fmaxf(ma, __shfl_xor_sync(~0u, ma, 1)); mb = fmaxf(mb, __shfl_xor_sync(~0u, mb, 1));
                    ma = fmaxf(ma, __shfl_xor_sync(~0u, ma, 2)); mb = fmaxf(mb, __shfl_xor_sync(~0u, mb, 2));
                    na = -ma * CS; nb = -mb * CS;
                }
                PROFC(8 + 3 * hf);
                {
                    if (hf == 0) mbar_wait(BAR(B_VRFULL), 0);
                    float o[16] = {}, rs[4] = {};
                    const uint32_t va = sb + OFF_Y + Y_VR + (kg0 + ((lane >> 3) & 1)) * 896 + (3 * w + (lane >> 4)) * 128 + (lane & 7) * 16;
#pragma unroll
                    for (int pp = 0; pp < 17; pp++) {
                        uint32_t B[8];
                        const uint32_t v = va + pp * 1792 + (pp == 16 || (pp >= 9 && kg0 + 2 * pp >= 32) ? Y_VOWN - 32 * 896 : 0);
                        ldsm4t(v, B); ldsm4t(v + 256, B + 4);
                        float e[8];
#pragma unroll
                        for (int i = 0; i < 8; i++) e[i] = ex2(fmaf(s[8 * pp + i], CS, ((i & 2) ? nb : na) + (pp < pmin ? NEG : 0.f)));
                        const uint32_t p0 = pack2(e[0], e[1]), p1 = pack2(e[2], e[3]), p2 = pack2(e[4], e[5]), p3 = pack2(e[6], e[7]);
                        mma16816(rs, p0, p1, p2, p3, 0x3F803F80u, 0x3F803F80u);
#pragma unroll
                        for (int g = 0; g < 4; g++) mma16816(o + 4 * g, p0, p1, p2, p3, B[2 * g], B[2 * g + 1]);
                    }
                    PROFC(9 + 3 * hf);
                    const float ia = rcp(rs[0]), ib = rcp(rs[2]);
                    uint32_t* og = g_o + (size_t)(2 * r + hf) * 14336 + (7 * j + 3 * w) * 256 + wi * 64 + lane;
#pragma unroll
                    for (int g = 0; g < 4; g++) {
                        if ((g == 3 - 3 * w) ? ((q >> 1) == w) : true) {
                            og[g * 256] = pack2(o[4 * g] * ia, o[4 * g + 1] * ia);
                            og[g * 256 + 32] = pack2(o[4 * g + 2] * ib, o[4 * g + 3] * ib);
                        }
                    }
                    warp_arrive(BAR(B_PUB + 2 + hf));
                    PROFC(10 + 3 * hf);
                }
            }
        }
        uint32_t x1p[14];
        COORDS
        constexpr uint64_t DT = dconst(1024, 128, 0);
        if (RUN(4)) {
            float ac[28];
            const uint64_t ad = mkdesc(sb + (w ? OFF_Y + HALF : OFF_X), DT), bd = mkdesc(sb + OFF_X + HALF, DB128) + kh;
            WAIT(B_WOFULL, 0);
            WAIT(B_MOD2, 0);
            WAIT(B_GFULL + w, 0);
            PROFC(28);
            reg_def<28>(ac);
#pragma unroll 1
            for (int u = 0; u < 4; u++) {
                WG_FENCE();
#pragma unroll
                for (int i = 0; i < 7; i++) wgmma_ss_56<1>(ac, ad + (7 * u + i) * 128, bd + (7 * u + i) * 128, (u | i) != 0);
            }
            WG_COMMIT();
            WG_WAIT(0);
            reg_fence<28>(ac);
            PROFC(14);
            __syncwarp();
            if (lane < 3) mbar_arrive(BAR(B_EMPTY + 3 + lane));
            if (lane < 3 && w == 0) mbar_arrive(BAR(B_EMPTY + lane));
            float s1a = 0.f, s2a = 0.f, s1b = 0.f, s2b = 0.f;
            uint32_t* xo = g_x1 + (size_t)(2 * r + w) * 14336 + 7 * j * 256 + wi * 64 + lane;
#pragma unroll
            for (int g = 0; g < 7; g++) {
                const float2 ga = *(const float2*)(smem + M_G + (8 * g + 2 * q) * 4);
                x1p[2 * g] = pack2(fmaf(ga.x, ac[4 * g], bf_lo(xr[2 * g])), fmaf(ga.y, ac[4 * g + 1], bf_hi(xr[2 * g])));
                x1p[2 * g + 1] = pack2(fmaf(ga.x, ac[4 * g + 2], bf_lo(xr[2 * g + 1])), fmaf(ga.y, ac[4 * g + 3], bf_hi(xr[2 * g + 1])));
                xo[g * 256] = x1p[2 * g]; xo[g * 256 + 32] = x1p[2 * g + 1];
                const float u0 = bf_lo(x1p[2 * g]), u1 = bf_hi(x1p[2 * g]), u2 = bf_lo(x1p[2 * g + 1]), u3 = bf_hi(x1p[2 * g + 1]);
                s1a += u0 + u1; s2a += u0 * u0 + u1 * u1; s1b += u2 + u3; s2b += u2 * u2 + u3 * u3;
            }
            float ka = (q & 1) ? s2a : s1a, kb2 = (q & 1) ? s2b : s1b;
            ka += __shfl_xor_sync(~0u, (q & 1) ? s1a : s2a, 1); kb2 += __shfl_xor_sync(~0u, (q & 1) ? s1b : s2b, 1);
            const float kk = ((q & 2) ? kb2 : ka) + __shfl_xor_sync(~0u, (q & 2) ? ka : kb2, 2);
            ((float*)g_st)[(((2 * r + w) * 8 + j) * 64 + 16 * wi + lr + 4 * (q & 2)) * 2 + (q & 1)] = kk;
            __syncwarp();
            if (lane < 2) mbar_arrive(BAR(B_PUB + 4 + w));
        } else reg_def<14>(x1p);
        PROFC(15);
        uint32_t h2a[32], h2b[24];
        if (RUN(6)) {
            const int fa = pass_f(fs, 0), fb = pass_f(fs, 1), fc = pass_f(fs, 2);
            uint32_t* h2g = g_h2 + (size_t)r * (224 * 512) + (8 * w + 2 * wi) * 32 + lane;
            const uint64_t a0 = mkdesc(sb + OFF_Y + w * HALF, DT);
            {
                WAIT(B_GFULL + 2 + w, 0);
                PROFC(16);
                float2 sa = make_float2(0.f, 0.f), sbb = sa;
#pragma unroll
                for (int jj = 0; jj < 8; jj++) {
                    const float2 u = lds2f(sb + OFF_X + X_STAT + w * 4096 + (jj * 64 + 16 * wi + lr) * 8), v = lds2f(sb + OFF_X + X_STAT + w * 4096 + (jj * 64 + 16 * wi + lr + 8) * 8);
                    sa.x += u.x; sa.y += u.y; sbb.x += v.x; sbb.y += v.y;
                }
                warp_arrive(BAR(B_EMPTY + 6));
                uint32_t ra2, na2, rb2, nb2;
                ln_coeffs(sa.x * (1.f / DM), sa.y * (1.f / DM), ra2, na2);
                ln_coeffs(sbb.x * (1.f / DM), sbb.y * (1.f / DM), rb2, nb2);
                const uint32_t ha = sb + OFF_Y + w * HALF + (lane >> 4) * 1024 + (2 * wi + ((lane >> 3) & 1)) * 128 + (lane & 7) * 16;
                const uint32_t sta = sb + M_ST + q * 16;
                auto prep = [&](int s, uint32_t* f) {
                    uint32_t x[8];
                    ldsm4(ha + s * 4096, x); ldsm4(ha + s * 4096 + 2048, x + 4);
                    const uint4 st[2] = {lds4(sta + s * 128), lds4(sta + s * 128 + 64)};
#pragma unroll
                    for (int i = 0; i < 2; i++) {
                        f[4 * i] = hfma2(hfma2(x[4 * i], ra2, na2), st[i].x, st[i].y); f[4 * i + 1] = hfma2(hfma2(x[4 * i + 1], rb2, nb2), st[i].x, st[i].y);
                        f[4 * i + 2] = hfma2(hfma2(x[4 * i + 2], ra2, na2), st[i].z, st[i].w); f[4 * i + 3] = hfma2(hfma2(x[4 * i + 3], rb2, nb2), st[i].z, st[i].w);
                    }
                    stsm4(ha + s * 4096, f[0], f[1], f[2], f[3]); stsm4(ha + s * 4096 + 2048, f[4], f[5], f[6], f[7]);
                };
                float ac[128];
                uint32_t fr[3][8];
                const uint64_t bx = mkdesc(sb, DB128);
                reg_def<128>(ac);
                prep(0, fr[0]);
                PROFC(17);
#pragma unroll
                for (int s = 0; s < 14; s++) {
                    const uint32_t* f = fr[s % 3];
                    const uint64_t bd = bx + (slot_off(s % 7) >> 4);
                    WAIT(B_FULL + s % 7, s >= 7);
                    WG_FENCE();
                    wgmma_rs_256<1>(ac, f[0], f[1], f[2], f[3], bd, s != 0);
                    wgmma_rs_256<1>(ac, f[4], f[5], f[6], f[7], bd + 128, 1);
                    WG_COMMIT();
                    if (s < 13) prep(s + 1, fr[(s + 1) % 3]);
                    if (s > 0) { WG_WAIT(1); warp_arrive(BAR(B_EMPTY + (s - 1) % 7)); }
                }
                PROFC(18);
                fence_async_smem();
                WG_WAIT(0);
                reg_fence<128>(ac);
                warp_arrive(BAR(B_EMPTY + 6));
#pragma unroll
                for (int g = 0; g < 16; g++) {
                    h2a[2 * g] = hmul2(pack2_relu(ac[4 * g], ac[4 * g + 1]), pack2(ac[64 + 4 * g], ac[64 + 4 * g + 1]));
                    h2a[2 * g + 1] = hmul2(pack2_relu(ac[4 * g + 2], ac[4 * g + 3]), pack2(ac[64 + 4 * g + 2], ac[64 + 4 * g + 3]));
                    h2g[(fa / 8 + g) * 512] = h2a[2 * g]; h2g[(fa / 8 + g) * 512 + 32] = h2a[2 * g + 1];
                }
                warp_arrive(BAR(B_PUB + 6));
                bar_sync(1 + w, 128);
            }
            PROFC(19);
            {
                float ac[64];
                reg_def<64>(ac);
                const uint64_t bx = mkdesc(sb, dconst(8192, 1024, 1));
#pragma unroll
                for (int s = 0; s < 7; s++) {
                    WAIT(B_FULL + s, 0);
                    const uint64_t ad = a0 + s * 512, bd = bx + (slot_off(s) >> 4);
                    WG_FENCE();
#pragma unroll
                    for (int k = 0; k < 4; k++) wgmma_ss_128<1>(ac, ad + k * 128, bd + k * 128, (s | k) != 0);
                    WG_COMMIT();
                    if (s > 0) { WG_WAIT(1); warp_arrive(BAR(B_EMPTY + s - 1)); }
                }
                WG_WAIT(0);
                reg_fence<64>(ac);
                warp_arrive(BAR(B_EMPTY + 6));
#pragma unroll
                for (int g = 0; g < 8; g++) {
                    h2b[2 * g] = hmul2(pack2_relu(ac[4 * g], ac[4 * g + 1]), pack2(ac[32 + 4 * g], ac[32 + 4 * g + 1]));
                    h2b[2 * g + 1] = hmul2(pack2_relu(ac[4 * g + 2], ac[4 * g + 3]), pack2(ac[32 + 4 * g + 2], ac[32 + 4 * g + 3]));
                    h2g[(fb / 8 + g) * 512] = h2b[2 * g]; h2g[(fb / 8 + g) * 512 + 32] = h2b[2 * g + 1];
                }
                warp_arrive(BAR(B_PUB + 7));
            }
            PROFC(27);
            {
                float ac[32];
                reg_def<32>(ac);
                const uint64_t bx = mkdesc(sb, dconst(4096, 512, 2));
#pragma unroll
                for (int s = 0; s < 7; s++) {
                    WAIT(B_FULL + s, 1);
                    const uint64_t ad = a0 + s * 512, bd = bx + (slot_off(s) >> 4);
                    WG_FENCE();
#pragma unroll
                    for (int k = 0; k < 4; k++) wgmma_ss_64<1>(ac, ad + k * 128, bd + k * 64, (s | k) != 0);
                    WG_COMMIT();
                    if (s > 0) { WG_WAIT(1); warp_arrive(BAR(B_EMPTY + s - 1)); }
                }
                WG_WAIT(0);
                reg_fence<32>(ac);
                __syncwarp();
                if (lane < 6) mbar_arrive(BAR(B_EMPTY + 6 + lane));
                PROFC(20);
#pragma unroll
                for (int g = 0; g < 4; g++) {
                    h2b[16 + 2 * g] = hmul2(pack2_relu(ac[4 * g], ac[4 * g + 1]), pack2(ac[16 + 4 * g], ac[16 + 4 * g + 1]));
                    h2b[16 + 2 * g + 1] = hmul2(pack2_relu(ac[4 * g + 2], ac[4 * g + 3]), pack2(ac[16 + 4 * g + 2], ac[16 + 4 * g + 3]));
                    h2g[(fc / 8 + g) * 512] = h2b[16 + 2 * g]; h2g[(fc / 8 + g) * 512 + 32] = h2b[16 + 2 * g + 1];
                }
                warp_arrive(BAR(B_PUB + 8));
                asm volatile("barrier.cluster.wait.aligned;" ::: "memory");
                if (lane == 0 && !sc) {
                    uint32_t rb;
                    asm volatile("mapa.shared::cluster.u32 %0, %1, %2;" : "=r"(rb) : "r"(BAR(B_PEER)), "r"(kh ^ 1));
                    asm volatile("mbarrier.arrive.relaxed.cluster.shared::cluster.b64 _, [%0];" ::"r"(rb) : "memory");
                }
            }
        } else { reg_def<32>(h2a); reg_def<24>(h2b); }
        PROFC(21);
        if (RUN(7)) {
            float ac[56];
            reg_def<56>(ac);
            constexpr uint64_t DAN = dconst(2048, 128, 0);
            const uint64_t bx = mkdesc(sb, DB128);
#pragma unroll
            for (int e = 0; e < 4; e++) {
                WAIT(B_FULL + e, 0);
                const uint64_t bd = bx + (slot_off(e) >> 4);
                const uint32_t* hh = e < 2 ? h2a + 16 * e : h2b + 16 * (e - 2);
                WG_FENCE();
#pragma unroll
                for (int k = 0; k < (e < 3 ? 4 : 2); k++) wgmma_rs_112<1>(ac, hh[4 * k], hh[4 * k + 1], hh[4 * k + 2], hh[4 * k + 3], bd + (k >> 1) * 512 + (k & 1) * 128, (e | k) != 0);
                WG_COMMIT();
                if (e > 0) { WG_WAIT(1); warp_arrive(BAR(B_EMPTY + e - 1)); }
            }
            PROFC(22);
            const uint64_t ax = mkdesc(sb + 8192 + w * 1024, DAN);
#pragma unroll
            for (int e = 4; e < 25; e++) {
                WAIT(B_FULL + e % 12, e >= 12 && e < 24);
                if (e == 16) PROFC(23);
                const uint64_t ad = ax + (slot_off(e % 12) >> 4), bd = bx + (slot_off(e % 12) >> 4);
                WG_FENCE();
                wgmma_ss_112<1>(ac, ad, bd, 1);
                wgmma_ss_112<1>(ac, ad + 256, bd + 128, 1);
                WG_COMMIT();
                if (e < 14) { WG_WAIT(1); warp_arrive(BAR(B_EMPTY + (e - 1) % 12)); }
            }
            mbar_wait_cluster(BAR(B_PEER), sc);
            WG_WAIT(0);
            reg_fence<56>(ac);
            PROFC(24);
            uint32_t rdst, rbar;
            asm volatile("mapa.shared::cluster.u32 %0, %1, %2;" : "=r"(rdst) : "r"(sb + OFF_Y + (5 + w) * 16384 + t * 16), "r"(kh ^ 1 ^ sc));
            asm volatile("mapa.shared::cluster.u32 %0, %1, %2;" : "=r"(rbar) : "r"(BAR(B_XCH + w)), "r"(kh ^ 1 ^ sc));
#define ACG(g, i) ac[4 * (((g) + 8) % 14) + (i)]
#pragma unroll
            for (int g = 0; g < 7; g++) {
                const float v0 = kh ? ACG(g, 0) : ACG(g + 7, 0), v1 = kh ? ACG(g, 1) : ACG(g + 7, 1);
                const float v2 = kh ? ACG(g, 2) : ACG(g + 7, 2), v3 = kh ? ACG(g, 3) : ACG(g + 7, 3);
                if (!sc) asm volatile("st.async.shared::cluster.mbarrier::complete_tx::bytes.v4.f32 [%0], {%1,%2,%3,%4}, [%5];"
                             ::"r"(rdst + g * 2048), "f"(v0), "f"(v1), "f"(v2), "f"(v3), "r"(rbar) : "memory");
            }
            mbar_wait_cluster(BAR(B_XCH + w), sc);
            PROFC(25);
            bf16* og = (sc ? (bf16*)(g_h2 + 16 * 224 * 512) : p.out + (size_t)128 * r * DM) + (size_t)ra * DM + 56 * j + 2 * q;
#pragma unroll
            for (int g = 0; g < 7; g++) {
                const uint4 rv = *(const uint4*)(smem + OFF_Y + (5 + w) * 16384 + t * 16 + g * 2048);
                const float2 gb = *(const float2*)(smem + M_G + 224 + (8 * g + 2 * q) * 4);
                const float v0 = (kh ? ACG(g + 7, 0) : ACG(g, 0)) + __uint_as_float(rv.x), v1 = (kh ? ACG(g + 7, 1) : ACG(g, 1)) + __uint_as_float(rv.y);
                const float v2 = (kh ? ACG(g + 7, 2) : ACG(g, 2)) + __uint_as_float(rv.z), v3 = (kh ? ACG(g + 7, 3) : ACG(g, 3)) + __uint_as_float(rv.w);
                *(uint32_t*)(og + 8 * g) = pack2(fmaf(gb.x, v0, bf_lo(x1p[2 * g])), fmaf(gb.y, v1, bf_hi(x1p[2 * g])));
                *(uint32_t*)(og + 8 * DM + 8 * g) = pack2(fmaf(gb.x, v2, bf_lo(x1p[2 * g + 1])), fmaf(gb.y, v3, bf_hi(x1p[2 * g + 1])));
            }
        }
        PROFC(26);
        bar_sync(1 + w, 128);
        if (wi == 0) warp_arrive(BAR(B_DONE));
    } else {
        const int lane = fresh_tid() & 31;
        const bool early = kh == 0, gemv = r < 14;
        const int mcol = early ? 16 * (4 * r + nq) : 2 * DM + 32 * (4 * r + nq);
        const uint32_t wmbuf = sb + OFF_Y + HALF;
        asm volatile("setmaxnreg.dec.sync.aligned.u32 56;");
        if (warp == 9) {
#pragma unroll
            for (int i = 56; i < 64; i++) init_e(BAR(i), 1);
            fence_async_smem();
        }
        if (warp == 8) { init_e(BAR(B_WMFULL), 2); fence_async_smem(); }
        bar_arrive(0, 384);
        asm volatile("barrier.cluster.arrive.relaxed.aligned;" ::: "memory");
        uint32_t target = 0;
        if (warp == 8) {
            if (!sc) {
                expect_e(BAR(B_WMFULL), gemv ? 28672 >> early : 0);
                if (early && gemv) { tma3_e(wmbuf, &p.wm, mcol, 0, 0, BAR(B_WMFULL)); tma3_e(wmbuf + 7168, &p.wm, mcol, 224, 0, BAR(B_WMFULL)); }
#pragma unroll 1
                for (int kb = 0; kb < 7; kb++) {
                    expect_e(BAR(B_XFULL + kb), 16384);
                    tma3_e(sb + OFF_X + kb * 16384, &p.xm, 64 * kb, 128 * r, 0, BAR(B_XFULL + kb));
                }
            }
#pragma unroll 1
            for (int mt = 0; mt < 4; mt++) {
                if (mt == 1) {
                    if (!early && gemv) {
#pragma unroll 1
                        for (int k = 0; k < 4; k++) tma3_e(wmbuf + k * 7168, &p.wm, mcol + (k >> 1) * 16, (k & 1) * 224, 0, BAR(B_WMFULL));
                    }
                    bar_sync(9, 384);
                    if (sc) return;
                    mbar_wait(BAR(B_MOD1), 0);
                    mbar_wait(BAR(B_WMFREE), 0);
                }
                if (mt == 2) mbar_wait(BAR(B_XFREE), 0);
                if (mt == 3) mbar_wait(BAR(B_VRFULL), 0);
                const uint32_t bar = BAR(mt == 3 ? B_WOFULL : B_FULLK + mt), dst = sb + (mt < 2 ? OFF_Y : OFF_X) + (mt & 1) * HALF;
                const int c0 = (mt < 2 ? DM + DM * mt : 0) + 56 * j - 8 * kh;
                if (!sc) {
                    expect_e(bar, HALF);
                    tma3_e(dst, mt == 3 ? &p.wo : &p.qkv, c0, 0, 0, bar);
                    tma3_e(dst + HALF / 2, mt == 3 ? &p.wo : &p.qkv, c0, 224, 0, bar);
                }
            }
            expect_e(BAR(B_XCH), 14336);
            expect_e(BAR(B_XCH + 1), 14336);
        } else {
            if (warp == 10 && !sc) {
                l2_prefetch_e((const char*)p.wqkv + (size_t)b * 9408, 9408);
                if (lane == 0) sts1(sb + M_EPOCH, atomicAdd(&g_ticket, 1u) / NCTA);
            }
            if (warp == 11) {
#pragma unroll
                for (int i = 0; i < 8; i++) {
                    const int wd = lane + 32 * i;
                    const uint32_t cb = i < 7 ? __ldg((const uint32_t*)p.c + wd) : 0u;
                    sts1(wmbuf + 28672 + (wd >> 3) * 32 + (wd & 3) * 8 + (wd & 4), pack2(silu_bf(cb & 0xFFFFu), silu_bf(cb >> 16)));
                }
            }
            bar_sync(9, 384);
            if (sc) return;
            target = lds1(sb + M_EPOCH) + 1;
            const uint32_t tag = target & 0xFFFFu;
            if (warp == 11) {
                warp_arrive(BAR(B_WMFULL));
                mbar_wait(BAR(B_GEMV), 0);
                float sum = 0.f;
#pragma unroll
                for (int i = 0; i < 8; i++) sum += *(const float*)(smem + OFF_Y + HALF + 29696 + (i * 32 + (early ? lane & 15 : lane)) * 4);
                const uint32_t word = (pack2(sum, 0.f) << 16) | tag;
                if (gemv) {
                    uint32_t* mg = g_mod + mcol + (early ? (lane & 15) + (lane >> 4) * 4 * 6 * DM : lane);
#pragma unroll
                    for (int i = 0; i < 8; i++) if (i < 4 || !early) st_relaxed(mg + i * 6 * DM, word);
                }
                warp_arrive(BAR(B_WMFREE));
            }
            const uint4* modp = (const uint4*)g_mod + (r & 7) * (6 * DM / 4);
            const bool p2 = warp == 11;
            mbar_wait(BAR(p2 ? B_PUB : B_XFULL + 4), 0);
#pragma unroll 1
            for (int it = p2 ? 0 : warp - 9; it < (p2 ? 2 : warp - 8); it++) {
                const int i0 = lane + 32 * it, imax = p2 ? 251 : 223;
                uint4 v[4];
#pragma unroll 1
                for (int n = 0;; n++) {
                    uint32_t bad = 0;
#pragma unroll
                    for (int k = 0; k < 4; k++) {
                        const int i = min(i0 + 64 * k, imax);
                        v[k] = ld_relaxed4(modp + (i < 224 ? (p2 ? 336 : 0) + i : (i < 238 ? 14 * j + i : 14 * j + i + 322)));
                        bad |= (v[k].x ^ tag) | (v[k].y ^ tag) | (v[k].z ^ tag) | (v[k].w ^ tag);
                    }
                    if (!__any_sync(~0u, bad & 0xFFFFu)) break;
                    if (n > SPIN_LIMIT) __trap();
                }
#pragma unroll
                for (int k = 0; k < 4; k++) {
                    const int i = min(i0 + 64 * k, imax);
                    if (i < 224) {
                        const int isc = i >= 112, c4 = i - 112 * isc;
                        const float one = isc ? 1.f : 0.f;
                        const uint32_t a = sb + M_ST + (c4 >> 2) * 64 + (c4 & 1) * 32 + (c4 & 2) * 4 + (isc ? 0 : 4);
                        sts1(a, pack2(bf_hi(v[k].x) + one, bf_hi(v[k].y) + one));
                        sts1(a + 16, pack2(bf_hi(v[k].z) + one, bf_hi(v[k].w) + one));
                    } else {
                        sts4(sb + M_G + (i - 224) * 16, make_uint4(v[k].x & 0xFFFF0000u, v[k].y & 0xFFFF0000u, v[k].z & 0xFFFF0000u, v[k].w & 0xFFFF0000u));
                    }
                }
                warp_arrive(BAR(p2 ? B_MOD2 : B_MOD1));
            }
            if (warp == 9) {
#pragma unroll 1
                for (int kv = 0; kv < 2; kv++) {
                    mbar_wait(BAR(B_PUB + kv), 0);
                    if (lane >= 1 && lane <= 2 && r >= lane) wait_flag(g_flag + kv * 128 + b - 8 * lane, target);
                    __syncwarp();
                    fence_async_global();
                    const uint32_t dst = sb + OFF_Y + (kv ? Y_VR : Y_K);
                    expect_e(BAR(B_KRFULL + kv), r >= 2 ? 28672 : r == 1 ? 14336 : 0);
                    if (r >= 2) bulk_e(dst, g_kv + (size_t)((b - 16) * 2 + kv) * 3584, 14336, BAR(B_KRFULL + kv));
                    if (r >= 1) bulk_e(dst + 14336, g_kv + (size_t)((b - 8) * 2 + kv) * 3584, 14336, BAR(B_KRFULL + kv));
                }
            } else if (warp == 11) {
                mbar_wait(BAR(B_VRFULL), 0);
                l2_prefetch_e((const char*)p.wg + (size_t)b * 12544, 12544);
                l2_prefetch_e((const char*)p.wu + (size_t)b * 12544, 12544);
                l2_prefetch_e((const char*)p.wd + (size_t)b * 12544, 12544);
            }
        }
        if (warp == 8 || warp == 11) {
            const int sec = warp == 11;
            if (sec) ring_loader<1>(p, sb, r, j); else ring_loader<0>(p, sb, r, j);
            mbar_wait(BAR(B_DONE), 0);
        } else if (warp == 9) {
#pragma unroll
            for (int ev = 0; ev < 4; ev++) expect_e(BAR(B_GFULL + ev), ev < 2 ? HALF : HALF + 4096);
            mbar_wait(BAR(B_PUB + 2), 0);
            const uint32_t* fp = g_flag + (2 + (lane >> 3)) * 128 + 8 * r + (lane & 7);
            const uint32_t* src = g_ox + (size_t)2 * r * 14336;
            const float2* ssrc = g_st + 2 * r * 512;
#pragma unroll 1
            for (int n = 0, ev = 0; ev < 4; n++) {
                if (ev == 1) mbar_wait(BAR(B_PUB + 3), 0);
                uint32_t ok = __ballot_sync(~0u, (int)(ld_relaxed(fp) - target) >= 0) >> (8 * ev);
                while ((ok & 0xFFu) == 0xFFu) {
                    asm volatile("fence.acquire.gpu;" ::: "memory");
                    fence_async_global();
                    const uint32_t bar = BAR(B_GFULL + ev);
                    bulk_e(sb + (ev == 0 ? OFF_X : OFF_Y + (ev & 1) * HALF), src + (ev >> 1) * (34 * 14336) + (ev & 1) * 14336, HALF, bar);
                    if (ev >= 2) bulk_e(sb + OFF_X + X_STAT + (ev & 1) * 4096, ssrc + (ev & 1) * 512, 4096, bar);
                    if (ev) PROFH(4 + ev);
                    ev++; ok >>= 8;
                }
                if (n > SPIN_LIMIT) __trap();
            }
#pragma unroll 1
            for (int ps = 0; ps < 3; ps++) {
                mbar_wait(BAR(B_PUB + 6 + ps), 0);
                if (lane < 4) wait_flag(g_flag + (6 + ps) * 128 + 8 * r + 2 * lane + kh, target);
                warp_arrive(BAR(B_HRDY + ps));
                PROFH(9 + ps);
            }
        } else {
            if (lane == 0) {
#pragma unroll 1
                for (int k = 0; k < 9; k++) {
                    mbar_wait(BAR(B_PUB + k), 0);
                    fence_gpu();
                    st_relaxed(g_flag + k * 128 + b, target);
                    if (k >= 3 && k <= 5) PROFH1(k - 3);
                }
            }
        }
    }
}

typedef CUresult (*EncodeFn)(CUtensorMap*, CUtensorMapDataType, cuuint32_t, void*, const cuuint64_t*, const cuuint64_t*, const cuuint32_t*,
                             const cuuint32_t*, CUtensorMapInterleave, CUtensorMapSwizzle, CUtensorMapL2promotion, CUtensorMapFloatOOBfill);

static void make_map(EncodeFn fn, CUtensorMap* m, const void* ptr, uint64_t d0, uint64_t d1, uint64_t d2, uint64_t s1, uint64_t s2,
                     uint32_t b0, uint32_t b1, uint32_t b2, CUtensorMapSwizzle sw) {
    cuuint64_t dims[3] = {d0, d1, d2}, strides[2] = {s1, s2};
    cuuint32_t box[3] = {b0, b1, b2}, es[3] = {1, 1, 1};
    CUresult rc = fn(m, CU_TENSOR_MAP_DATA_TYPE_BFLOAT16, 3, (void*)ptr, dims, strides, box, es, CU_TENSOR_MAP_INTERLEAVE_NONE, sw,
                     CU_TENSOR_MAP_L2_PROMOTION_L2_128B, CU_TENSOR_MAP_FLOAT_OOB_FILL_NONE);
    (void)rc;
}

extern "C" void kernel_launch(void* const* d_in, const int* in_sizes, int n_in, void* d_out, int out_size) {
    (void)in_sizes; (void)n_in; (void)out_size;
    static EncodeFn fn = nullptr;
    if (!fn) {
        cudaDriverEntryPointQueryResult st;
        cudaGetDriverEntryPoint("cuTensorMapEncodeTiled", (void**)&fn, cudaEnableDefault, &st);
        cudaFuncSetAttribute(fused_block_kernel, cudaFuncAttributeMaxDynamicSharedMemorySize, SMEM_BYTES);
    }
    Params p;
    p.x = (const bf16*)d_in[0];
    const bf16* wqkv = (const bf16*)d_in[1];
    p.wqkv = wqkv;
    p.wop = (const bf16*)d_in[2];
    p.wg = (const bf16*)d_in[4];
    p.wu = (const bf16*)d_in[5];
    p.wd = (const bf16*)d_in[6];
    p.c = (const bf16*)d_in[7];
    p.wmod = (const bf16*)d_in[8];
    p.out = (bf16*)d_out;
    p.zero = 0;
    make_map(fn, &p.wm, p.wmod, 2688, 448, 1, 5376, 5376 * 448, 16, 224, 1, CU_TENSOR_MAP_SWIZZLE_NONE);
    make_map(fn, &p.xm, p.x, 448, 2048, 1, 896, 896 * 2048, 64, 128, 1, CU_TENSOR_MAP_SWIZZLE_128B);
    make_map(fn, &p.qkv, wqkv, 1344, 448, 1, 2688, 2688 * 448, 64, 224, 1, CU_TENSOR_MAP_SWIZZLE_128B);
    make_map(fn, &p.wo, p.wop, 448, 448, 1, 896, 896 * 448, 64, 224, 1, CU_TENSOR_MAP_SWIZZLE_128B);
    make_map(fn, &p.ga, p.wg, 64, 448, 28, 3584, 128, 64, 32, 2, CU_TENSOR_MAP_SWIZZLE_128B);
    make_map(fn, &p.ua, p.wu, 64, 448, 28, 3584, 128, 64, 32, 2, CU_TENSOR_MAP_SWIZZLE_128B);
    make_map(fn, &p.gb, p.wg, 64, 448, 28, 3584, 128, 64, 64, 1, CU_TENSOR_MAP_SWIZZLE_128B);
    make_map(fn, &p.ub, p.wu, 64, 448, 28, 3584, 128, 64, 64, 1, CU_TENSOR_MAP_SWIZZLE_128B);
    make_map(fn, &p.gc, p.wg, 32, 448, 56, 3584, 64, 32, 64, 1, CU_TENSOR_MAP_SWIZZLE_64B);
    make_map(fn, &p.uc, p.wu, 32, 448, 56, 3584, 64, 32, 64, 1, CU_TENSOR_MAP_SWIZZLE_64B);
    make_map(fn, &p.dn, p.wd, 448, 1792, 1, 896, 896 * 1792, 64, 32, 1, CU_TENSOR_MAP_SWIZZLE_128B);
    fused_block_kernel<<<GRID, 384, SMEM_BYTES>>>(p);
}
```

```cpp
#include <cuda_runtime.h>
#include <cuda_bf16.h>
#include <cuda.h>
#include <stdint.h>

typedef __nv_bfloat16 bf16;

template<int TB> __device__ __forceinline__ void wgmma_rs_56(float* d, uint32_t a0, uint32_t a1, uint32_t a2, uint32_t a3, uint64_t db, int sd) {
  asm volatile("{\n.reg .pred p;\nsetp.ne.b32 p, %33, 0;\n"
    "wgmma.mma_async.sync.aligned.m64n56k16.f32.bf16.bf16 {%0,%1,%2,%3,%4,%5,%6,%7,%8,%9,%10,%11,%12,%13,%14,%15,%16,%17,%18,%19,%20,%21,%22,%23,%24,%25,%26,%27}, {%28,%29,%30,%31}, %32, p, 1, 1, %34;\n}\n"
    : "+f"(d[0]),"+f"(d[1]),"+f"(d[2]),"+f"(d[3]),"+f"(d[4]),"+f"(d[5]),"+f"(d[6]),"+f"(d[7]),"+f"(d[8]),"+f"(d[9]),"+f"(d[10]),"+f"(d[11]),"+f"(d[12]),"+f"(d[13]),"+f"(d[14]),"+f"(d[15]),"+f"(d[16]),"+f"(d[17]),"+f"(d[18]),"+f"(d[19]),"+f"(d[20]),"+f"(d[21]),"+f"(d[22]),"+f"(d[23]),"+f"(d[24]),"+f"(d[25]),"+f"(d[26]),"+f"(d[27])
    : "r"(a0), "r"(a1), "r"(a2), "r"(a3), "l"(db), "r"(sd), "n"(TB));
}
template<int TB> __device__ __forceinline__ void wgmma_ss_56(float* d, uint64_t da, uint64_t db, int sd) {
  asm volatile("{\n.reg .pred p;\nsetp.ne.b32 p, %30, 0;\n"
    "wgmma.mma_async.sync.aligned.m64n56k16.f32.bf16.bf16 {%0,%1,%2,%3,%4,%5,%6,%7,%8,%9,%10,%11,%12,%13,%14,%15,%16,%17,%18,%19,%20,%21,%22,%23,%24,%25,%26,%27}, %28, %29, p, 1, 1, 0, %31;\n}\n"
    : "+f"(d[0]),"+f"(d[1]),"+f"(d[2]),"+f"(d[3]),"+f"(d[4]),"+f"(d[5]),"+f"(d[6]),"+f"(d[7]),"+f"(d[8]),"+f"(d[9]),"+f"(d[10]),"+f"(d[11]),"+f"(d[12]),"+f"(d[13]),"+f"(d[14]),"+f"(d[15]),"+f"(d[16]),"+f"(d[17]),"+f"(d[18]),"+f"(d[19]),"+f"(d[20]),"+f"(d[21]),"+f"(d[22]),"+f"(d[23]),"+f"(d[24]),"+f"(d[25]),"+f"(d[26]),"+f"(d[27])
    : "l"(da), "l"(db), "r"(sd), "n"(TB));
}
template<int TB> __device__ __forceinline__ void wgmma_rs_256(float* d, uint32_t a0, uint32_t a1, uint32_t a2, uint32_t a3, uint64_t db, int sd) {
  asm volatile("{\n.reg .pred p;\nsetp.ne.b32 p, %133, 0;\n"
    "wgmma.mma_async.sync.aligned.m64n256k16.f32.bf16.bf16 {%0,%1,%2,%3,%4,%5,%6,%7,%8,%9,%10,%11,%12,%13,%14,%15,%16,%17,%18,%19,%20,%21,%22,%23,%24,%25,%26,%27,%28,%29,%30,%31,%32,%33,%34,%35,%36,%37,%38,%39,%40,%41,%42,%43,%44,%45,%46,%47,%48,%49,%50,%51,%52,%53,%54,%55,%56,%57,%58,%59,%60,%61,%62,%63,%64,%65,%66,%67,%68,%69,%70,%71,%72,%73,%74,%75,%76,%77,%78,%79,%80,%81,%82,%83,%84,%85,%86,%87,%88,%89,%90,%91,%92,%93,%94,%95,%96,%97,%98,%99,%100,%101,%102,%103,%104,%105,%106,%107,%108,%109,%110,%111,%112,%113,%114,%115,%116,%117,%118,%119,%120,%121,%122,%123,%124,%125,%126,%127}, {%128,%129,%130,%131}, %132, p, 1, 1, %134;\n}\n"
    : "+f"(d[0]),"+f"(d[1]),"+f"(d[2]),"+f"(d[3]),"+f"(d[4]),"+f"(d[5]),"+f"(d[6]),"+f"(d[7]),"+f"(d[8]),"+f"(d[9]),"+f"(d[10]),"+f"(d[11]),"+f"(d[12]),"+f"(d[13]),"+f"(d[14]),"+f"(d[15]),"+f"(d[16]),"+f"(d[17]),"+f"(d[18]),"+f"(d[19]),"+f"(d[20]),"+f"(d[21]),"+f"(d[22]),"+f"(d[23]),"+f"(d[24]),"+f"(d[25]),"+f"(d[26]),"+f"(d[27]),"+f"(d[28]),"+f"(d[29]),"+f"(d[30]),"+f"(d[31]),"+f"(d[32]),"+f"(d[33]),"+f"(d[34]),"+f"(d[35]),"+f"(d[36]),"+f"(d[37]),"+f"(d[38]),"+f"(d[39]),"+f"(d[40]),"+f"(d[41]),"+f"(d[42]),"+f"(d[43]),"+f"(d[44]),"+f"(d[45]),"+f"(d[46]),"+f"(d[47]),"+f"(d[48]),"+f"(d[49]),"+f"(d[50]),"+f"(d[51]),"+f"(d[52]),"+f"(d[53]),"+f"(d[54]),"+f"(d[55]),"+f"(d[56]),"+f"(d[57]),"+f"(d[58]),"+f"(d[59]),"+f"(d[60]),"+f"(d[61]),"+f"(d[62]),"+f"(d[63]),"+f"(d[64]),"+f"(d[65]),"+f"(d[66]),"+f"(d[67]),"+f"(d[68]),"+f"(d[69]),"+f"(d[70]),"+f"(d[71]),"+f"(d[72]),"+f"(d[73]),"+f"(d[74]),"+f"(d[75]),"+f"(d[76]),"+f"(d[77]),"+f"(d[78]),"+f"(d[79]),"+f"(d[80]),"+f"(d[81]),"+f"(d[82]),"+f"(d[83]),"+f"(d[84]),"+f"(d[85]),"+f"(d[86]),"+f"(d[87]),"+f"(d[88]),"+f"(d[89]),"+f"(d[90]),"+f"(d[91]),"+f"(d[92]),"+f"(d[93]),"+f"(d[94]),"+f"(d[95]),"+f"(d[96]),"+f"(d[97]),"+f"(d[98]),"+f"(d[99]),"+f"(d[100]),"+f"(d[101]),"+f"(d[102]),"+f"(d[103]),"+f"(d[104]),"+f"(d[105]),"+f"(d[106]),"+f"(d[107]),"+f"(d[108]),"+f"(d[109]),"+f"(d[110]),"+f"(d[111]),"+f"(d[112]),"+f"(d[113]),"+f"(d[114]),"+f"(d[115]),"+f"(d[116]),"+f"(d[117]),"+f"(d[118]),"+f"(d[119]),"+f"(d[120]),"+f"(d[121]),"+f"(d[122]),"+f"(d[123]),"+f"(d[124]),"+f"(d[125]),"+f"(d[126]),"+f"(d[127])
    : "r"(a0), "r"(a1), "r"(a2), "r"(a3), "l"(db), "r"(sd), "n"(TB));
}
template<int TB> __device__ __forceinline__ void wgmma_ss_128(float* d, uint64_t da, uint64_t db, int sd) {
  asm volatile("{\n.reg .pred p;\nsetp.ne.b32 p, %66, 0;\n"
    "wgmma.mma_async.sync.aligned.m64n128k16.f32.bf16.bf16 {%0,%1,%2,%3,%4,%5,%6,%7,%8,%9,%10,%11,%12,%13,%14,%15,%16,%17,%18,%19,%20,%21,%22,%23,%24,%25,%26,%27,%28,%29,%30,%31,%32,%33,%34,%35,%36,%37,%38,%39,%40,%41,%42,%43,%44,%45,%46,%47,%48,%49,%50,%51,%52,%53,%54,%55,%56,%57,%58,%59,%60,%61,%62,%63}, %64, %65, p, 1, 1, 0, %67;\n}\n"
    : "+f"(d[0]),"+f"(d[1]),"+f"(d[2]),"+f"(d[3]),"+f"(d[4]),"+f"(d[5]),"+f"(d[6]),"+f"(d[7]),"+f"(d[8]),"+f"(d[9]),"+f"(d[10]),"+f"(d[11]),"+f"(d[12]),"+f"(d[13]),"+f"(d[14]),"+f"(d[15]),"+f"(d[16]),"+f"(d[17]),"+f"(d[18]),"+f"(d[19]),"+f"(d[20]),"+f"(d[21]),"+f"(d[22]),"+f"(d[23]),"+f"(d[24]),"+f"(d[25]),"+f"(d[26]),"+f"(d[27]),"+f"(d[28]),"+f"(d[29]),"+f"(d[30]),"+f"(d[31]),"+f"(d[32]),"+f"(d[33]),"+f"(d[34]),"+f"(d[35]),"+f"(d[36]),"+f"(d[37]),"+f"(d[38]),"+f"(d[39]),"+f"(d[40]),"+f"(d[41]),"+f"(d[42]),"+f"(d[43]),"+f"(d[44]),"+f"(d[45]),"+f"(d[46]),"+f"(d[47]),"+f"(d[48]),"+f"(d[49]),"+f"(d[50]),"+f"(d[51]),"+f"(d[52]),"+f"(d[53]),"+f"(d[54]),"+f"(d[55]),"+f"(d[56]),"+f"(d[57]),"+f"(d[58]),"+f"(d[59]),"+f"(d[60]),"+f"(d[61]),"+f"(d[62]),"+f"(d[63])
    : "l"(da), "l"(db), "r"(sd), "n"(TB));
}
template<int TB> __device__ __forceinline__ void wgmma_ss_64(float* d, uint64_t da, uint64_t db, int sd) {
  asm volatile("{\n.reg .pred p;\nsetp.ne.b32 p, %34, 0;\n"
    "wgmma.mma_async.sync.aligned.m64n64k16.f32.bf16.bf16 {%0,%1,%2,%3,%4,%5,%6,%7,%8,%9,%10,%11,%12,%13,%14,%15,%16,%17,%18,%19,%20,%21,%22,%23,%24,%25,%26,%27,%28,%29,%30,%31}, %32, %33, p, 1, 1, 0, %35;\n}\n"
    : "+f"(d[0]),"+f"(d[1]),"+f"(d[2]),"+f"(d[3]),"+f"(d[4]),"+f"(d[5]),"+f"(d[6]),"+f"(d[7]),"+f"(d[8]),"+f"(d[9]),"+f"(d[10]),"+f"(d[11]),"+f"(d[12]),"+f"(d[13]),"+f"(d[14]),"+f"(d[15]),"+f"(d[16]),"+f"(d[17]),"+f"(d[18]),"+f"(d[19]),"+f"(d[20]),"+f"(d[21]),"+f"(d[22]),"+f"(d[23]),"+f"(d[24]),"+f"(d[25]),"+f"(d[26]),"+f"(d[27]),"+f"(d[28]),"+f"(d[29]),"+f"(d[30]),"+f"(d[31])
    : "l"(da), "l"(db), "r"(sd), "n"(TB));
}
template<int TB> __device__ __forceinline__ void wgmma_ss_112(float* d, uint64_t da, uint64_t db, int sd) {
  asm volatile("{\n.reg .pred p;\nsetp.ne.b32 p, %58, 0;\n"
    "wgmma.mma_async.sync.aligned.m64n112k16.f32.bf16.bf16 {%0,%1,%2,%3,%4,%5,%6,%7,%8,%9,%10,%11,%12,%13,%14,%15,%16,%17,%18,%19,%20,%21,%22,%23,%24,%25,%26,%27,%28,%29,%30,%31,%32,%33,%34,%35,%36,%37,%38,%39,%40,%41,%42,%43,%44,%45,%46,%47,%48,%49,%50,%51,%52,%53,%54,%55}, %56, %57, p, 1, 1, 0, %59;\n}\n"
    : "+f"(d[0]),"+f"(d[1]),"+f"(d[2]),"+f"(d[3]),"+f"(d[4]),"+f"(d[5]),"+f"(d[6]),"+f"(d[7]),"+f"(d[8]),"+f"(d[9]),"+f"(d[10]),"+f"(d[11]),"+f"(d[12]),"+f"(d[13]),"+f"(d[14]),"+f"(d[15]),"+f"(d[16]),"+f"(d[17]),"+f"(d[18]),"+f"(d[19]),"+f"(d[20]),"+f"(d[21]),"+f"(d[22]),"+f"(d[23]),"+f"(d[24]),"+f"(d[25]),"+f"(d[26]),"+f"(d[27]),"+f"(d[28]),"+f"(d[29]),"+f"(d[30]),"+f"(d[31]),"+f"(d[32]),"+f"(d[33]),"+f"(d[34]),"+f"(d[35]),"+f"(d[36]),"+f"(d[37]),"+f"(d[38]),"+f"(d[39]),"+f"(d[40]),"+f"(d[41]),"+f"(d[42]),"+f"(d[43]),"+f"(d[44]),"+f"(d[45]),"+f"(d[46]),"+f"(d[47]),"+f"(d[48]),"+f"(d[49]),"+f"(d[50]),"+f"(d[51]),"+f"(d[52]),"+f"(d[53]),"+f"(d[54]),"+f"(d[55])
    : "l"(da), "l"(db), "r"(sd), "n"(TB));
}
template<int TB> __device__ __forceinline__ void wgmma_rs_112(float* d, uint32_t a0, uint32_t a1, uint32_t a2, uint32_t a3, uint64_t db, int sd) {
  asm volatile("{\n.reg .pred p;\nsetp.ne.b32 p, %61, 0;\n"
    "wgmma.mma_async.sync.aligned.m64n112k16.f32.bf16.bf16 {%0,%1,%2,%3,%4,%5,%6,%7,%8,%9,%10,%11,%12,%13,%14,%15,%16,%17,%18,%19,%20,%21,%22,%23,%24,%25,%26,%27,%28,%29,%30,%31,%32,%33,%34,%35,%36,%37,%38,%39,%40,%41,%42,%43,%44,%45,%46,%47,%48,%49,%50,%51,%52,%53,%54,%55}, {%56,%57,%58,%59}, %60, p, 1, 1, %62;\n}\n"
    : "+f"(d[0]),"+f"(d[1]),"+f"(d[2]),"+f"(d[3]),"+f"(d[4]),"+f"(d[5]),"+f"(d[6]),"+f"(d[7]),"+f"(d[8]),"+f"(d[9]),"+f"(d[10]),"+f"(d[11]),"+f"(d[12]),"+f"(d[13]),"+f"(d[14]),"+f"(d[15]),"+f"(d[16]),"+f"(d[17]),"+f"(d[18]),"+f"(d[19]),"+f"(d[20]),"+f"(d[21]),"+f"(d[22]),"+f"(d[23]),"+f"(d[24]),"+f"(d[25]),"+f"(d[26]),"+f"(d[27]),"+f"(d[28]),"+f"(d[29]),"+f"(d[30]),"+f"(d[31]),"+f"(d[32]),"+f"(d[33]),"+f"(d[34]),"+f"(d[35]),"+f"(d[36]),"+f"(d[37]),"+f"(d[38]),"+f"(d[39]),"+f"(d[40]),"+f"(d[41]),"+f"(d[42]),"+f"(d[43]),"+f"(d[44]),"+f"(d[45]),"+f"(d[46]),"+f"(d[47]),"+f"(d[48]),"+f"(d[49]),"+f"(d[50]),"+f"(d[51]),"+f"(d[52]),"+f"(d[53]),"+f"(d[54]),"+f"(d[55])
    : "r"(a0), "r"(a1), "r"(a2), "r"(a3), "l"(db), "r"(sd), "n"(TB));
}

constexpr int DM = 448;
constexpr int NCTA = 128;
#define MAPPING 1
#define GRID 132
#define PINGPONG 0
#define WIN 4
#define WIN_END 25
#define MAP_S 4
constexpr int SPIN_LIMIT = 1 << 22;

constexpr uint32_t OFF_X = 0, OFF_Y = 114688, OFF_MISC = 229376, SMEM_BYTES = 232448;
constexpr uint32_t Y_VR = 0, Y_K = 28672, Y_KOWN = 57344, Y_VOWN = 71680, Y_Q = 86016;
constexpr uint32_t HALF = 57344;
constexpr uint32_t M_BAR = OFF_MISC;
constexpr uint32_t M_ST = OFF_MISC + 512;
constexpr uint32_t M_G = OFF_MISC + 2304;
constexpr uint32_t M_EPOCH = OFF_MISC + 3040;
enum { B_XFULL = 0, B_FULLK = 7, B_FULLV = 8, B_FULLQ, B_KRFULL, B_VRFULL, B_WOFULL, B_XCH, B_FULL = 16, B_MOD1 = 28, B_MOD2, B_WMFULL,
       B_EMPTY = 32, B_XFREE = B_EMPTY + 12, B_GEMV, B_PEER,
       B_PUB = 47,
       B_WMFREE = 56, B_HRDY, B_GFULL = B_HRDY + 3, B_DONE = 31 };
constexpr uint32_t X_STAT = 49152;

__device__ uint32_t g_ticket;
__device__ __align__(128) uint32_t g_mod[8 * 6 * DM];
__device__ __align__(128) uint32_t g_flag[9 * 16 * 8];
__device__ __align__(128) uint32_t g_kv[17 * 8 * 2 * 3584];
__device__ __align__(128) uint32_t g_ox[2 * 34 * 14336];
#define g_o g_ox
#define g_x1 (g_ox + 34 * 14336)
__device__ __align__(128) float2 g_st[34 * 8 * 64];
__device__ __align__(128) uint32_t g_h2[17 * 224 * 512];
#define PROFH(id)
#define PROFH1(id)
#define PROFC(id)

struct alignas(64) Params {
    CUtensorMap wm, xm, qkv, wo, ga, ua, gb, ub, gc, uc, dn;
    const bf16 *x, *c, *wqkv, *wmod, *wg, *wu, *wd, *wop;
    bf16* out;
    uint32_t zero;
};

__device__ __forceinline__ void mbar_init(uint32_t bar, int cnt) { asm volatile("mbarrier.init.shared::cta.b64 [%0], %1;" ::"r"(bar), "r"(cnt) : "memory"); }
__device__ __forceinline__ void mbar_expect_tx(uint32_t bar, uint32_t bytes) { asm volatile("mbarrier.arrive.expect_tx.shared::cta.b64 _, [%0], %1;" ::"r"(bar), "r"(bytes) : "memory"); }
__device__ __forceinline__ void mbar_arrive(uint32_t bar) { asm volatile("mbarrier.arrive.shared::cta.b64 _, [%0];" ::"r"(bar) : "memory"); }
__device__ __forceinline__ void mbar_wait(uint32_t bar, uint32_t parity) {
    uint32_t ok; int n = 0;
    do {
        asm volatile("{\n.reg .pred p;\nmbarrier.try_wait.parity.shared::cta.b64 p, [%1], %2;\nselp.u32 %0, 1, 0, p;\n}" : "=r"(ok) : "r"(bar), "r"(parity) : "memory");
        if (++n > SPIN_LIMIT) __trap();
    } while (!ok);
}
__device__ __forceinline__ void mbar_wait_c(uint32_t bar, uint32_t parity) {
    asm volatile("{\n.reg .pred p;\nWL:\nmbarrier.try_wait.parity.shared::cta.b64 p, [%0], %1;\n@!p bra WL;\n}" ::"r"(bar), "r"(parity) : "memory");
}
__device__ __forceinline__ void mbar_wait_cluster(uint32_t bar, uint32_t parity) {
    uint32_t ok; int n = 0;
    do {
        asm volatile("{\n.reg .pred p;\nmbarrier.try_wait.parity.acquire.cluster.shared::cta.b64 p, [%1], %2;\nselp.u32 %0, 1, 0, p;\n}" : "=r"(ok) : "r"(bar), "r"(parity) : "memory");
        if (++n > SPIN_LIMIT) __trap();
    } while (!ok);
}
__device__ __forceinline__ void warp_arrive(uint32_t bar) {
    __syncwarp();
    asm volatile("{\n.reg .pred p;\nelect.sync _|p, 0xffffffff;\n@p mbarrier.arrive.shared::cta.b64 _, [%0];\n}" ::"r"(bar) : "memory");
}
__device__ __forceinline__ int opaque(int v) { return __shfl_sync(~0u, v, 0); }
__device__ __forceinline__ int fresh_tid() { int v; asm volatile("mov.u32 %0, %%tid.x;" : "=r"(v)); return v; }
__device__ __forceinline__ void bar_sync(int id, int n) { asm volatile("bar.sync %0, %1;" ::"r"(id), "r"(n) : "memory"); }
__device__ __forceinline__ void bar_arrive(int id, int n) { asm volatile("bar.arrive %0, %1;" ::"r"(id), "r"(n) : "memory"); }
__device__ __forceinline__ void fence_async_smem() { asm volatile("fence.proxy.async.shared::cta;" ::: "memory"); }
__device__ __forceinline__ void fence_async_global() { asm volatile("fence.proxy.async.global;" ::: "memory"); }
__device__ __forceinline__ void fence_gpu() { asm volatile("fence.release.gpu;" ::: "memory"); }
__device__ __forceinline__ void tma3(uint32_t dst, const CUtensorMap* m, int c0, int c1, int c2, uint32_t bar) {
    asm volatile("cp.async.bulk.tensor.3d.shared::cluster.global.mbarrier::complete_tx::bytes [%0], [%1, {%3, %4, %5}], [%2];"
                 ::"r"(dst), "l"(m), "r"(bar), "r"(c0), "r"(c1), "r"(c2) : "memory");
}
__device__ __forceinline__ void bulk_load(uint32_t dst, const void* src, uint32_t bytes, uint32_t bar) {
    asm volatile("cp.async.bulk.shared::cluster.global.mbarrier::complete_tx::bytes [%0], [%1], %2, [%3];" ::"r"(dst), "l"(src), "r"(bytes), "r"(bar) : "memory");
}
__device__ __forceinline__ void expect_e(uint32_t bar, uint32_t bytes) {
    asm volatile("{\n.reg .pred p;\nelect.sync _|p, 0xffffffff;\n@p mbarrier.arrive.expect_tx.shared::cta.b64 _, [%0], %1;\n}" ::"r"(bar), "r"(bytes) : "memory");
}
__device__ __forceinline__ void tma3_e(uint32_t dst, const CUtensorMap* m, int c0, int c1, int c2, uint32_t bar) {
    asm volatile("{\n.reg .pred p;\nelect.sync _|p, 0xffffffff;\n@p cp.async.bulk.tensor.3d.shared::cluster.global.mbarrier::complete_tx::bytes [%0], [%1, {%3, %4, %5}], [%2];\n}"
                 ::"r"(dst), "l"(m), "r"(bar), "r"(c0), "r"(c1), "r"(c2) : "memory");
}
__device__ __forceinline__ void bulk_e(uint32_t dst, const void* src, uint32_t bytes, uint32_t bar) {
    asm volatile("{\n.reg .pred p;\nelect.sync _|p, 0xffffffff;\n@p cp.async.bulk.shared::cluster.global.mbarrier::complete_tx::bytes [%0], [%1], %2, [%3];\n}"
                 ::"r"(dst), "l"(src), "r"(bytes), "r"(bar) : "memory");
}
__device__ __forceinline__ void init_e(uint32_t bar, int cnt) {
    asm volatile("{\n.reg .pred p;\nelect.sync _|p, 0xffffffff;\n@p mbarrier.init.shared::cta.b64 [%0], %1;\n}" ::"r"(bar), "r"(cnt) : "memory");
}
__device__ __forceinline__ void l2_prefetch_e(const void* src, uint32_t bytes) {
    asm volatile("{\n.reg .pred p;\nelect.sync _|p, 0xffffffff;\n@p cp.async.bulk.prefetch.L2.global [%0], %1;\n}" ::"l"(src), "r"(bytes) : "memory");
}
__device__ __forceinline__ uint32_t ld_relaxed(const uint32_t* p) { uint32_t v; asm volatile("ld.relaxed.gpu.global.u32 %0, [%1];" : "=r"(v) : "l"(p) : "memory"); return v; }
__device__ __forceinline__ void st_relaxed(uint32_t* p, uint32_t v) { asm volatile("st.relaxed.gpu.global.u32 [%0], %1;" ::"l"(p), "r"(v) : "memory"); }
__device__ __forceinline__ uint4 ld_relaxed4(const uint4* p) { uint4 v; asm volatile("ld.relaxed.gpu.global.v4.u32 {%0,%1,%2,%3}, [%4];" : "=r"(v.x), "=r"(v.y), "=r"(v.z), "=r"(v.w) : "l"(p) : "memory"); return v; }
__device__ __forceinline__ void st_relaxed4(uint4* p, uint4 v) { asm volatile("st.relaxed.gpu.global.v4.u32 [%0], {%1,%2,%3,%4};" ::"l"(p), "r"(v.x), "r"(v.y), "r"(v.z), "r"(v.w) : "memory"); }
__device__ __forceinline__ uint4 ldg_nc4(const void* p) { uint4 v; asm volatile("ld.global.nc.L1::no_allocate.v4.u32 {%0,%1,%2,%3}, [%4];" : "=r"(v.x), "=r"(v.y), "=r"(v.z), "=r"(v.w) : "l"(p)); return v; }
__device__ __forceinline__ uint32_t ldg_nc(const void* p) { uint32_t v; asm volatile("ld.global.nc.u32 %0, [%1];" : "=r"(v) : "l"(p)); return v; }
__device__ __forceinline__ uint32_t ld_acquire(const uint32_t* p) { uint32_t v; asm volatile("ld.acquire.gpu.global.u32 %0, [%1];" : "=r"(v) : "l"(p) : "memory"); return v; }
__device__ __forceinline__ uint4 lds4(uint32_t a) { uint4 v; asm volatile("ld.shared.v4.u32 {%0,%1,%2,%3}, [%4];" : "=r"(v.x), "=r"(v.y), "=r"(v.z), "=r"(v.w) : "r"(a) : "memory"); return v; }
__device__ __forceinline__ float2 lds2f(uint32_t a) { float2 v; asm volatile("ld.shared.v2.f32 {%0,%1}, [%2];" : "=f"(v.x), "=f"(v.y) : "r"(a) : "memory"); return v; }
__device__ __forceinline__ uint32_t lds1(uint32_t a) { uint32_t v; asm volatile("ld.shared.u32 %0, [%1];" : "=r"(v) : "r"(a) : "memory"); return v; }
__device__ __forceinline__ void sts4(uint32_t a, uint4 v) { asm volatile("st.shared.v4.u32 [%0], {%1,%2,%3,%4};" ::"r"(a), "r"(v.x), "r"(v.y), "r"(v.z), "r"(v.w) : "memory"); }
__device__ __forceinline__ void sts2(uint32_t a, uint32_t x, uint32_t y) { asm volatile("st.shared.v2.u32 [%0], {%1,%2};" ::"r"(a), "r"(x), "r"(y) : "memory"); }
__device__ __forceinline__ void sts1(uint32_t a, uint32_t v) { asm volatile("st.shared.u32 [%0], %1;" ::"r"(a), "r"(v) : "memory"); }
__device__ __forceinline__ void stsm4(uint32_t a, uint32_t r0, uint32_t r1, uint32_t r2, uint32_t r3) {
    asm volatile("stmatrix.sync.aligned.m8n8.x4.shared.b16 [%0], {%1,%2,%3,%4};" ::"r"(a), "r"(r0), "r"(r1), "r"(r2), "r"(r3));
}
__device__ __forceinline__ uint32_t pack2(float lo, float hi) { uint32_t r; asm("cvt.rn.bf16x2.f32 %0, %1, %2;" : "=r"(r) : "f"(hi), "f"(lo)); return r; }
__device__ __forceinline__ uint32_t pack2_relu(float lo, float hi) { uint32_t r; asm("cvt.rn.relu.bf16x2.f32 %0, %1, %2;" : "=r"(r) : "f"(hi), "f"(lo)); return r; }
__device__ __forceinline__ uint32_t hfma2(uint32_t a, uint32_t b, uint32_t c) { uint32_t r; asm("fma.rn.bf16x2 %0, %1, %2, %3;" : "=r"(r) : "r"(a), "r"(b), "r"(c)); return r; }
__device__ __forceinline__ uint32_t hmul2(uint32_t a, uint32_t b) { uint32_t r; asm("mul.rn.bf16x2 %0, %1, %2;" : "=r"(r) : "r"(a), "r"(b)); return r; }
__device__ __forceinline__ float bf_lo(uint32_t v) { return __uint_as_float(v << 16); }
__device__ __forceinline__ float bf_hi(uint32_t v) { return __uint_as_float(v & 0xFFFF0000u); }
__device__ __forceinline__ float bf_round(float v) { return bf_lo(pack2(v, 0.f)); }
__device__ __forceinline__ float ex2(float x) { float r; asm("ex2.approx.ftz.f32 %0, %1;" : "=f"(r) : "f"(x)); return r; }
__device__ __forceinline__ void mma16816(float* d, uint32_t a0, uint32_t a1, uint32_t a2, uint32_t a3, uint32_t b0, uint32_t b1) {
    asm("mma.sync.aligned.m16n8k16.row.col.f32.bf16.bf16.f32 {%0,%1,%2,%3}, {%4,%5,%6,%7}, {%8,%9}, {%0,%1,%2,%3};"
        : "+f"(d[0]), "+f"(d[1]), "+f"(d[2]), "+f"(d[3]) : "r"(a0), "r"(a1), "r"(a2), "r"(a3), "r"(b0), "r"(b1));
}
__device__ __forceinline__ void mma16816_first(float* d, uint32_t a0, uint32_t a1, uint32_t a2, uint32_t a3, uint32_t b0, uint32_t b1) {
    asm volatile("mma.sync.aligned.m16n8k16.row.col.f32.bf16.bf16.f32 {%0,%1,%2,%3}, {%4,%5,%6,%7}, {%8,%9}, {%10,%10,%10,%10};"
        : "=f"(d[0]), "=f"(d[1]), "=f"(d[2]), "=f"(d[3]) : "r"(a0), "r"(a1), "r"(a2), "r"(a3), "r"(b0), "r"(b1), "f"(0.f));
}
__device__ __forceinline__ void mma16816_v(float* d, uint32_t a0, uint32_t a1, uint32_t a2, uint32_t a3, uint32_t b0, uint32_t b1) {
    asm volatile("mma.sync.aligned.m16n8k16.row.col.f32.bf16.bf16.f32 {%0,%1,%2,%3}, {%4,%5,%6,%7}, {%8,%9}, {%0,%1,%2,%3};"
        : "+f"(d[0]), "+f"(d[1]), "+f"(d[2]), "+f"(d[3]) : "r"(a0), "r"(a1), "r"(a2), "r"(a3), "r"(b0), "r"(b1));
}
__device__ __forceinline__ void mma1688(float* d, uint32_t a0, uint32_t a1, uint32_t b0) {
    asm("mma.sync.aligned.m16n8k8.row.col.f32.bf16.bf16.f32 {%0,%1,%2,%3}, {%4,%5}, {%6}, {%0,%1,%2,%3};"
        : "+f"(d[0]), "+f"(d[1]), "+f"(d[2]), "+f"(d[3]) : "r"(a0), "r"(a1), "r"(b0));
}
__device__ __forceinline__ void ldsm4(uint32_t a, uint32_t* r) {
    asm volatile("ldmatrix.sync.aligned.m8n8.x4.shared.b16 {%0,%1,%2,%3}, [%4];" : "=r"(r[0]), "=r"(r[1]), "=r"(r[2]), "=r"(r[3]) : "r"(a));
}
__device__ __forceinline__ void ldsm4t(uint32_t a, uint32_t* r) {
    asm volatile("ldmatrix.sync.aligned.m8n8.x4.trans.shared.b16 {%0,%1,%2,%3}, [%4];" : "=r"(r[0]), "=r"(r[1]), "=r"(r[2]), "=r"(r[3]) : "r"(a));
}
__device__ __forceinline__ float rcp(float x) { float r; asm("rcp.approx.ftz.f32 %0, %1;" : "=f"(r) : "f"(x)); return r; }
__device__ __forceinline__ uint2 ld_relaxed2(const void* p) { uint2 v; asm volatile("ld.relaxed.gpu.global.v2.u32 {%0,%1}, [%2];" : "=r"(v.x), "=r"(v.y) : "l"(p) : "memory"); return v; }
__device__ __forceinline__ void st_relaxed2(void* p, uint32_t x, uint32_t y) { asm volatile("st.relaxed.gpu.global.v2.u32 [%0], {%1,%2};" ::"l"(p), "r"(max(x, 1u)), "r"(max(y, 1u)) : "memory"); }
__device__ __forceinline__ constexpr uint64_t dconst(uint32_t lbo, uint32_t sbo, uint32_t swz) {
    return ((uint64_t)(lbo >> 4) << 16) | ((uint64_t)(sbo >> 4) << 32) | ((uint64_t)swz << 62);
}
__device__ __forceinline__ uint64_t mkdesc(uint32_t addr, uint64_t c) { return c | (uint64_t)((addr & 0x3FFFF) >> 4); }
#define WG_FENCE() asm volatile("wgmma.fence.sync.aligned;" ::: "memory")
#define WG_COMMIT() asm volatile("wgmma.commit_group.sync.aligned;" ::: "memory")
#define WG_WAIT(n) asm volatile("wgmma.wait_group.sync.aligned %0;" ::"n"(n) : "memory")
template <int N> __device__ __forceinline__ void reg_fence(float* d) {
#pragma unroll
    for (int i = 0; i < N; i++) asm volatile("" : "+f"(d[i])::"memory");
}
template <int N> __device__ __forceinline__ void reg_def(float* d) {
#pragma unroll
    for (int i = 0; i < N; i++) asm volatile("" : "=f"(d[i]));
}
template <int N> __device__ __forceinline__ void reg_def(uint32_t* d) {
#pragma unroll
    for (int i = 0; i < N; i++) asm volatile("" : "=r"(d[i]));
}
__device__ __forceinline__ bool is_unset(uint4 v) { return min(min(v.x, v.y), min(v.z, v.w)) == 0u; }
__device__ __forceinline__ uint4 nz4(uint32_t a, uint32_t b, uint32_t c, uint32_t d) { return make_uint4(max(a, 1u), max(b, 1u), max(c, 1u), max(d, 1u)); }
__device__ __forceinline__ void wait_flag(const uint32_t* p, uint32_t target) {
    int n = 0;
    while ((int)(ld_relaxed(p) - target) < 0) { if (++n > SPIN_LIMIT) __trap(); }
    asm volatile("fence.acquire.gpu;" ::: "memory");
}
__device__ __forceinline__ float silu_bf(uint32_t cbits) {
    const float c = __uint_as_float(cbits << 16);
    return bf_round(__fdividef(c, 1.f + fminf(ex2(-1.4426950408889634f * c), 1e30f)));
}
__device__ __forceinline__ void gemv_part(uint32_t wmbuf, int npanel, int wp, int lane) {
    const uint32_t wa = wmbuf + wp * 512 + (8 * (lane >> 4) + (lane & 7)) * 32 + ((lane >> 3) & 1) * 16;
    uint2 B[4];
#pragma unroll
    for (int i = 0; i < 4; i++) { const float2 v = lds2f(wmbuf + 28672 + (wp + 8 * i) * 32 + (lane & 3) * 8); B[i] = make_uint2(__float_as_uint(v.x), __float_as_uint(v.y)); }
#pragma unroll 1
    for (int pn = 0; pn < npanel; pn++) {
        float d[4] = {};
        uint32_t A[16];
#pragma unroll
        for (int i = 0; i < 4; i++) ldsm4t(wa + pn * 14336 + (i < 3 || wp < 4 ? i : 0) * 4096, A + 4 * i);
#pragma unroll
        for (int i = 0; i < 4; i++) mma16816(d, A[4 * i], A[4 * i + 1], A[4 * i + 2], A[4 * i + 3], B[i].x, B[i].y);
        if ((lane & 3) == 0) {
            sts1(wmbuf + 29696 + (wp * 32 + pn * 16 + (lane >> 2)) * 4, __float_as_uint(d[0]));
            sts1(wmbuf + 29696 + (wp * 32 + pn * 16 + 8 + (lane >> 2)) * 4, __float_as_uint(d[2]));
        }
    }
}
__device__ __forceinline__ int pass_f(int fs, int ps) { return 224 * fs + ((fs & 1) ? (ps == 0 ? 96 : ps == 1 ? 32 : 0) : (ps == 0 ? 0 : ps == 1 ? 128 : 192)); }
__device__ __forceinline__ constexpr uint32_t slot_off(int l) { return (l < 3 || l > 6 ? l : l == 6 ? 3 : l + 1) * 16384; }
__device__ __forceinline__ void ln_coeffs(float mean, float msq, uint32_t& r2, uint32_t& n2) {
    const float rs = bf_round(rsqrtf(fmaxf(msq - mean * mean, 0.f) + 1e-5f));
    r2 = pack2(rs, rs);
    n2 = pack2(-mean * rs, -mean * rs);
}

template <int sec> __device__ __forceinline__ void ring_loader(const Params& p, uint32_t sb_, int r_, int j_) {
    const uint32_t sb = opaque(sb_);
    const int r = opaque(r_), j = opaque(j_), nq = j >> 1, fs = 4 * (j & 1) + nq;
    const int fa = pass_f(fs, 0), fb = pass_f(fs, 1), fc = pass_f(fs, 2);
#define BAR(i) (sb + M_BAR + 8 * (i))
#define kh (j & 1)
            int sl = 0;
#pragma unroll 1
            for (int s = 0; s < 28; s++) {
                if (s >= 1 && s < 6) mbar_wait(BAR(B_FULL + s - 1), 0);
                const int ps = s < 14 ? 0 : s < 21 ? 1 : 2;
                const uint32_t half = ps < 2 ? 8192 : 4096;
                mbar_wait(BAR(B_EMPTY + sl), (s >= 7 && s < 14) || s >= 21);
                expect_e(BAR(B_FULL + sl), half);
                tma3_e(sb + slot_off(sl) + sec * half, &p.ga + 2 * ps + sec, 0, ps ? 64 * sl : 32 * s, ps == 0 ? fa >> 6 : ps == 1 ? fb >> 6 : fc >> 5, BAR(B_FULL + sl));
                sl = sl == 6 ? 0 : sl + 1;
            }
            if (!sec) PROFH(3);
#pragma unroll 1
            for (int e = 0; e < 4; e++) {
                const uint32_t dst = sb + slot_off(e) + sec * 8192, bar = BAR(B_FULL + e);
                const int f = (e < 2 ? fa + 64 * e : e == 2 ? fb : fc) + 32 * sec;
                mbar_wait(BAR(B_EMPTY + e), 0);
                expect_e(bar, e == 3 && sec ? 0 : 8192);
                if (!(e == 3 && sec)) { tma3_e(dst, &p.dn, 112 * nq + 48, f, 0, bar); tma3_e(dst + 4096, &p.dn, 112 * nq, f, 0, bar); }
            }
            sl = 4;
            int e = 4;
#pragma unroll 1
            for (int grp = 0; grp < 9; grp++) {
                const int ps = grp >= 6 ? 2 : grp >= 3 ? 1 : 0;
                int sidx = grp - 3 * ps;
                if (sec && sidx == 0) { mbar_wait(BAR(B_HRDY + ps), 0); fence_async_global(); }
                sidx += sidx >= nq;
                int f = pass_f(4 * kh + sidx, ps);
#pragma unroll 1
                for (int k = 4 >> ps; k > 0; k--, e++, f += 32) {
                    const uint32_t dst = sb + slot_off(sl), bar = BAR(B_FULL + sl);
                    mbar_wait(BAR(B_EMPTY + sl), e >= 12 && e < 24);
                    if (e < WIN_END) mbar_wait(BAR(B_FULL + (sl >= WIN ? sl - WIN : sl + 12 - WIN)), e - WIN >= 12);
                    expect_e(bar, 8192);
                    if (!sec) { tma3_e(dst, &p.dn, 112 * nq + 48, f, 0, bar); tma3_e(dst + 4096, &p.dn, 112 * nq, f, 0, bar); }
                    else bulk_e(dst + 8192, g_h2 + (size_t)r * (224 * 512) + f * 64, 8192, bar);
                    sl = sl == 11 ? 0 : sl + 1;
                }
            }
            if (!sec) PROFH(4);
}

__global__ void __cluster_dims__(2, 1, 1) __launch_bounds__(384, 1) fused_block_kernel(const __grid_constant__ Params p) {
    extern __shared__ __align__(1024) unsigned char smem[];
    const uint32_t sb = (uint32_t)__cvta_generic_to_shared(smem);
    const int tid = threadIdx.x, lane = tid & 31, warp = __shfl_sync(~0u, tid >> 5, 0);
    const int m = blockIdx.x >> 1;
    int r, nq;
    {
        int g, i;
        if (m < MAP_S) { g = m < 4 ? 15 : 16; i = m & 3; }
        else if (m < MAP_S + 32) { g = (m - MAP_S) & 7; i = (m - MAP_S) >> 3; }
        else if (m < MAP_S + 60) { i = (m - MAP_S - 32) / 7; g = 8 + (m - MAP_S - 32) - 7 * i; }
        else { g = 16; i = m & 3; }
        r = g; nq = i;
    }
    const int j = opaque(2 * nq + (blockIdx.x & 1)), b = 8 * r + j, fs = 4 * kh + nq;
    const uint32_t sc = r == 16;
    if (lane == 0 && warp < 9 && warp != 6 && warp != 7) {
        const int i0 = warp == 8 ? 0 : 8 + 8 * warp, cnt = warp == 0 || warp == 8 ? 1 : warp < 3 ? 2 : 8;
#pragma unroll
        for (int k = 0; k < 8; k++) if (i0 + k != B_WMFULL) mbar_init(BAR(i0 + k), cnt);
        asm volatile("fence.mbarrier_init.release.cluster;" ::: "memory");
        fence_async_smem();
    }

    if (warp < 8) {
        const int w = warp >> 2, wi = warp & 3;
#define COORDS const int t = fresh_tid() & 127, lane = t & 31, q = lane & 3, lr = lane >> 2, ra = 64 * w + 16 * wi + lr; \
        const uint32_t lx = (lane >> 4) ^ (lane & 7), mrow = (64 * w + 16 * wi + ((lane >> 3) & 1) * 8 + (lane & 7)) * 128; \
        (void)q; (void)lr; (void)ra; (void)lx; (void)mrow;
        const int sid = 2 * (j & 3) + w;
#define RUN(k) (!sc || sid == (k))
#define WAIT(i, par) mbar_wait_c(BAR(i), (par) | sc)
        constexpr uint64_t DB128 = dconst(4096, 1024, 1);
        bar_arrive(9, 384);
        bar_sync(0, 384);
        asm volatile("barrier.cluster.arrive.relaxed.aligned;" ::: "memory");
        asm volatile("setmaxnreg.inc.sync.aligned.u32 224;");
        PROFC(0);
        uint32_t xr[16];
        {
            COORDS
            uint32_t h[112];
            if (RUN(0)) {
                float ds[4] = {}, da[2][4] = {}, db[2][4] = {};
                const uint32_t ONE2 = 0x3F803F80u;
                if (kh == 0) { WAIT(B_WMFULL, 0); gemv_part(sb + OFF_Y + HALF, 1, warp, lane); warp_arrive(BAR(B_GEMV)); }
#pragma unroll
                for (int kb = 0; kb < 7; kb++) {
                    WAIT(B_XFULL + kb, 0);
#pragma unroll
                    for (int k4 = 0; k4 < 4; k4++) ldsm4(sb + OFF_X + mrow + kb * 16384 + (((2 * k4) ^ lx) << 4), h + 16 * kb + 4 * k4);
#pragma unroll
                    for (int k4 = 0; k4 < 4; k4++) {
                        const uint32_t* f = h + 16 * kb + 4 * k4;
                        mma16816(ds, f[0], f[1], f[2], f[3], ONE2, ONE2);
                        mma1688(da[0], f[0], f[1], f[0]); mma1688(db[0], f[0], f[1], f[1]);
                        mma1688(da[1], f[2], f[3], f[2]); mma1688(db[1], f[2], f[3], f[3]);
                    }
                }
#pragma unroll
                for (int i = 0; i < 4; i++) {
                    const int ch = 7 * j + 2 * i + (lane >> 4);
                    ldsm4(sb + OFF_X + mrow + (ch >> 3) * 16384 + (((ch ^ lane) & 7) << 4), xr + 4 * i);
                }
                warp_arrive(BAR(B_XFREE));
                float qa = (lr & 1) ? da[0][1] + da[1][1] : da[0][0] + da[1][0];
                float qb = (lr & 1) ? db[0][3] + db[1][3] : db[0][2] + db[1][2];
                const int src = (lane & ~3) | (lr >> 1);
                qa = __shfl_sync(~0u, qa, src);
                qb = __shfl_sync(~0u, qb, src);
                uint32_t ra2, na2, rb2, nb2;
                ln_coeffs(ds[0] * (1.f / DM), qa * (1.f / DM), ra2, na2);
                ln_coeffs(ds[2] * (1.f / DM), qb * (1.f / DM), rb2, nb2);
#pragma unroll
                for (int i = 0; i < 112; i += 2) { h[i] = hfma2(h[i], ra2, na2); h[i + 1] = hfma2(h[i + 1], rb2, nb2); }
                if (kh == 1) { WAIT(B_WMFULL, 0); gemv_part(sb + OFF_Y + HALF, 2, warp, lane); warp_arrive(BAR(B_GEMV)); }
            } else { reg_def<112>(h); reg_def<16>(xr); }
            PROFC(1);
            if (RUN(1)) {
                float ak[28], av[28], aq[28];
                uint32_t kp[14], vp[14];
                const uint64_t bk0 = mkdesc(sb + OFF_Y, DB128) + kh, bv0 = mkdesc(sb + OFF_Y + HALF, DB128) + kh, bq0 = mkdesc(sb + OFF_X, DB128) + kh;
                uint32_t* kvg = g_kv + (size_t)(b * 2) * 3584 + (8 * w + 2 * wi) * 224 + lane;
                WAIT(B_FULLK, 0);
                WAIT(B_MOD1, 0);
                PROFC(2);
                reg_def<28>(ak);
#pragma unroll
                for (int g4 = 0; g4 < 4; g4++) {
#pragma unroll
                    for (int ks = 7 * g4; ks < 7 * g4 + 7; ks++) {
                        const uint4 st = *(const uint4*)(smem + M_ST + ks * 64 + q * 16);
                        h[4 * ks] = hfma2(h[4 * ks], st.x, st.y); h[4 * ks + 1] = hfma2(h[4 * ks + 1], st.x, st.y);
                        h[4 * ks + 2] = hfma2(h[4 * ks + 2], st.z, st.w); h[4 * ks + 3] = hfma2(h[4 * ks + 3], st.z, st.w);
                    }
                    WG_FENCE();
#pragma unroll
                    for (int ks = 7 * g4; ks < 7 * g4 + 7; ks++) wgmma_rs_56<1>(ak, h[4 * ks], h[4 * ks + 1], h[4 * ks + 2], h[4 * ks + 3], bk0 + ks * 128, ks != 0);
                }
                WG_COMMIT();
                PROFC(3);
                WAIT(B_FULLV, 0);
                reg_def<28>(av);
                WG_FENCE();
#pragma unroll
                for (int ks = 0; ks < 8; ks++) wgmma_rs_56<1>(av, h[4 * ks], h[4 * ks + 1], h[4 * ks + 2], h[4 * ks + 3], bv0 + ks * 128, ks != 0);
                WG_COMMIT();
                WG_WAIT(1);
                reg_fence<28>(ak);
#pragma unroll
                for (int g = 0; g < 7; g++) {
                    kp[2 * g] = pack2(ak[4 * g], ak[4 * g + 1]); kp[2 * g + 1] = pack2(ak[4 * g + 2], ak[4 * g + 3]);
                    kvg[g * 32] = kp[2 * g]; kvg[224 + g * 32] = kp[2 * g + 1];
                }
                warp_arrive(BAR(B_PUB));
                PROFC(4);
                WG_FENCE();
#pragma unroll
                for (int ks = 8; ks < 28; ks++) wgmma_rs_56<1>(av, h[4 * ks], h[4 * ks + 1], h[4 * ks + 2], h[4 * ks + 3], bv0 + ks * 128, 1);
                WG_COMMIT();
                WAIT(B_FULLQ, 0);
                reg_def<28>(aq);
                WG_FENCE();
#pragma unroll
                for (int ks = 0; ks < 8; ks++) wgmma_rs_56<1>(aq, h[4 * ks], h[4 * ks + 1], h[4 * ks + 2], h[4 * ks + 3], bq0 + ks * 128, ks != 0);
                WG_COMMIT();
                WG_WAIT(1);
                reg_fence<28>(av);
#pragma unroll
                for (int g = 0; g < 7; g++) {
                    vp[2 * g] = pack2(av[4 * g], av[4 * g + 1]); vp[2 * g + 1] = pack2(av[4 * g + 2], av[4 * g + 3]);
                    kvg[3584 + g * 32] = vp[2 * g]; kvg[3584 + 224 + g * 32] = vp[2 * g + 1];
                }
                warp_arrive(BAR(B_PUB + 1));
                PROFC(5);
                WG_FENCE();
#pragma unroll
                for (int ks = 8; ks < 28; ks++) wgmma_rs_56<1>(aq, h[4 * ks], h[4 * ks + 1], h[4 * ks + 2], h[4 * ks + 3], bq0 + ks * 128, 1);
                WG_COMMIT();
                WAIT(B_PUB + 1, 0);
                const uint32_t ko = sb + OFF_Y + Y_KOWN + (8 * w + 2 * wi) * 896 + lane * 4;
                const uint32_t qo = sb + OFF_Y + Y_Q + (8 * w + 2 * wi) * 1024 + lane * 4;
#pragma unroll
                for (int g = 0; g < 7; g++) {
                    sts1(ko + g * 128, kp[2 * g]); sts1(ko + 896 + g * 128, kp[2 * g + 1]);
                    sts1(ko + (Y_VOWN - Y_KOWN) + g * 128, vp[2 * g]); sts1(ko + (Y_VOWN - Y_KOWN) + 896 + g * 128, vp[2 * g + 1]);
                }
                WG_WAIT(0);
                reg_fence<28>(aq);
                __syncwarp();
                if (lane < 3 && w == 1) mbar_arrive(BAR(B_EMPTY + lane));
#pragma unroll
                for (int g = 0; g < 7; g++) {
                    const uint32_t q0 = pack2(aq[4 * g], aq[4 * g + 1]), q1 = pack2(aq[4 * g + 2], aq[4 * g + 3]);
                    if (g == 3) {
                        sts1(qo + 3 * 128, q < 2 ? q0 : 0u); sts1(qo + 1024 + 3 * 128, q < 2 ? q1 : 0u);
                        sts1(qo + 4 * 128, q < 2 ? 0u : q0); sts1(qo + 1024 + 4 * 128, q < 2 ? 0u : q1);
                    } else {
                        const int ch = g < 3 ? g : g + 1;
                        sts1(qo + ch * 128, q0); sts1(qo + 1024 + ch * 128, q1);
                    }
                }
                if (!sc) bar_sync(3, 256);
            }
        }
        PROFC(6);
        WAIT(B_KRFULL, 0);
        PROFC(7);
        if (RUN(2)) {
#pragma unroll 1
            for (int hf = sc; hf < 2; hf++) {
                COORDS
                float s[136];
                float na = 0.f, nb = 0.f;
                const float CS = 0.18898223650461361f * 1.4426950408889634f;
                const int kg0 = 8 * hf + 2 * wi;
                const int pmin = 16 - 8 * r - 4 * hf - wi;
                const float NEG = __int_as_float(0xFF800000);
                {
                    uint32_t F[8];
                    const uint32_t qa = sb + OFF_Y + Y_Q + (kg0 + ((lane >> 3) & 1)) * 1024 + (4 * w + (lane >> 4)) * 128 + (lane & 7) * 16;
                    ldsm4(qa, F); ldsm4(qa + 256, F + 4);
                    uint32_t ka = sb + OFF_Y + Y_K + kg0 * 896 + (3 * w + (lane >> 3)) * 128 + (lane & 7) * 16;
#pragma unroll
                    for (int g = 0; g < 34; g++) {
                        uint32_t B[4];
                        if (g >= 12 && g % 4 == 0) ka += __float_as_uint(s[4 * (g - 12)]) & p.zero;
                        ldsm4(ka + g * 896, B);
                        mma16816_first(s + 4 * g, F[0], F[1], F[2], F[3], B[0], B[1]);
                        mma16816_v(s + 4 * g, F[4], F[5], F[6], F[7], B[2], B[3]);
                    }
                    const bool c0 = 2 * q > lr, c1 = 2 * q + 1 > lr;
                    if (!c0) { s[0] = NEG; s[6] = NEG; }
                    if (!c1) { s[1] = NEG; s[7] = NEG; }
                    s[2] = NEG; s[3] = NEG;
                    if (c0) { s[128] = NEG; s[134] = NEG; }
                    if (c1) { s[129] = NEG; s[135] = NEG; }
                    s[132] = NEG; s[133] = NEG;
                    float ma = NEG, mb = NEG;
#pragma unroll
                    for (int pp = 0; pp < 17; pp++) {
                        const float* e = s + 8 * pp;
                        const float bias = pp < pmin ? NEG : 0.f;
                        ma = fmaxf(ma, fmaxf(fmaxf(e[0], e[1]), fmaxf(e[4], e[5])) + bias);
                        mb = fmaxf(mb, fmaxf(fmaxf(e[2], e[3]), fmaxf(e[6], e[7])) + bias);
                    }
                    ma = fmaxf(ma, __shfl_xor_sync(~0u, ma, 1)); mb = fmaxf(mb, __shfl_xor_sync(~0u, mb, 1));
                    ma = fmaxf(ma, __shfl_xor_sync(~0u, ma, 2)); mb = fmaxf(mb, __shfl_xor_sync(~0u, mb, 2));
                    na = -ma * CS; nb = -mb * CS;
                }
                PROFC(8 + 3 * hf);
                {
                    WAIT(B_VRFULL, 0);
                    float o[16] = {}, rs[4] = {};
                    const uint32_t va = sb + OFF_Y + Y_VR + (kg0 + ((lane >> 3) & 1)) * 896 + (3 * w + (lane >> 4)) * 128 + (lane & 7) * 16;
#pragma unroll
                    for (int pp = 0; pp < 17; pp++) {
                        uint32_t B[8];
                        const uint32_t v = va + pp * 1792 + (pp == 16 || (pp >= 9 && kg0 + 2 * pp >= 32) ? Y_VOWN - 32 * 896 : 0);
                        ldsm4t(v, B); ldsm4t(v + 256, B + 4);
                        float e[8];
#pragma unroll
                        for (int i = 0; i < 8; i++) e[i] = ex2(fmaf(s[8 * pp + i], CS, ((i & 2) ? nb : na) + (pp < pmin ? NEG : 0.f)));
                        const uint32_t p0 = pack2(e[0], e[1]), p1 = pack2(e[2], e[3]), p2 = pack2(e[4], e[5]), p3 = pack2(e[6], e[7]);
                        mma16816(rs, p0, p1, p2, p3, 0x3F803F80u, 0x3F803F80u);
#pragma unroll
                        for (int g = 0; g < 4; g++) mma16816(o + 4 * g, p0, p1, p2, p3, B[2 * g], B[2 * g + 1]);
                    }
                    PROFC(9 + 3 * hf);
                    const float ia = rcp(rs[0]), ib = rcp(rs[2]);
                    uint32_t* og = g_o + (size_t)(2 * r + hf) * 14336 + (7 * j + 3 * w) * 256 + wi * 64 + lane;
#pragma unroll
                    for (int g = 0; g < 4; g++) {
                        if ((g == 3 - 3 * w) ? ((q >> 1) == w) : true) {
                            og[g * 256] = pack2(o[4 * g] * ia, o[4 * g + 1] * ia);
                            og[g * 256 + 32] = pack2(o[4 * g + 2] * ib, o[4 * g + 3] * ib);
                        }
                    }
                    warp_arrive(BAR(B_PUB + 2 + hf));
                    PROFC(10 + 3 * hf);
                }
            }
        }
        uint32_t x1p[14];
        COORDS
        constexpr uint64_t DT = dconst(1024, 128, 0);
        if (RUN(4)) {
            float ac[28];
            const uint64_t ad = mkdesc(sb + (w ? OFF_Y + HALF : OFF_X), DT), bd = mkdesc(sb + OFF_X + HALF, DB128) + kh;
            WAIT(B_WOFULL, 0);
            WAIT(B_MOD2, 0);
            WAIT(B_GFULL + w, 0);
            PROFC(28);
            reg_def<28>(ac);
#pragma unroll 1
            for (int u = 0; u < 4; u++) {
                WG_FENCE();
#pragma unroll
                for (int i = 0; i < 7; i++) wgmma_ss_56<1>(ac, ad + (7 * u + i) * 128, bd + (7 * u + i) * 128, (u | i) != 0);
            }
            WG_COMMIT();
            WG_WAIT(0);
            reg_fence<28>(ac);
            PROFC(14);
            __syncwarp();
            if (lane < 3) mbar_arrive(BAR(B_EMPTY + 3 + lane));
            if (lane < 3 && w == 0) mbar_arrive(BAR(B_EMPTY + lane));
            float s1a = 0.f, s2a = 0.f, s1b = 0.f, s2b = 0.f;
            uint32_t* xo = g_x1 + (size_t)(2 * r + w) * 14336 + 7 * j * 256 + wi * 64 + lane;
#pragma unroll
            for (int g = 0; g < 7; g++) {
                const float2 ga = *(const float2*)(smem + M_G + (8 * g + 2 * q) * 4);
                x1p[2 * g] = pack2(fmaf(ga.x, ac[4 * g], bf_lo(xr[2 * g])), fmaf(ga.y, ac[4 * g + 1], bf_hi(xr[2 * g])));
                x1p[2 * g + 1] = pack2(fmaf(ga.x, ac[4 * g + 2], bf_lo(xr[2 * g + 1])), fmaf(ga.y, ac[4 * g + 3], bf_hi(xr[2 * g + 1])));
                xo[g * 256] = x1p[2 * g]; xo[g * 256 + 32] = x1p[2 * g + 1];
                const float u0 = bf_lo(x1p[2 * g]), u1 = bf_hi(x1p[2 * g]), u2 = bf_lo(x1p[2 * g + 1]), u3 = bf_hi(x1p[2 * g + 1]);
                s1a += u0 + u1; s2a += u0 * u0 + u1 * u1; s1b += u2 + u3; s2b += u2 * u2 + u3 * u3;
            }
            float ka = (q & 1) ? s2a : s1a, kb2 = (q & 1) ? s2b : s1b;
            ka += __shfl_xor_sync(~0u, (q & 1) ? s1a : s2a, 1); kb2 += __shfl_xor_sync(~0u, (q & 1) ? s1b : s2b, 1);
            const float kk = ((q & 2) ? kb2 : ka) + __shfl_xor_sync(~0u, (q & 2) ? ka : kb2, 2);
            ((float*)g_st)[(((2 * r + w) * 8 + j) * 64 + 16 * wi + lr + 4 * (q & 2)) * 2 + (q & 1)] = kk;
            __syncwarp();
            if (lane < 2) mbar_arrive(BAR(B_PUB + 4 + w));
        } else reg_def<14>(x1p);
        PROFC(15);
        uint32_t h2a[32], h2b[24];
        if (RUN(6)) {
            const int fa = pass_f(fs, 0), fb = pass_f(fs, 1), fc = pass_f(fs, 2);
            uint32_t* h2g = g_h2 + (size_t)r * (224 * 512) + (8 * w + 2 * wi) * 32 + lane;
            const uint64_t a0 = mkdesc(sb + OFF_Y + w * HALF, DT);
            {
                WAIT(B_GFULL + 2 + w, 0);
                PROFC(16);
                float2 sa = make_float2(0.f, 0.f), sbb = sa;
#pragma unroll
                for (int jj = 0; jj < 8; jj++) {
                    const float2 u = lds2f(sb + OFF_X + X_STAT + w * 4096 + (jj * 64 + 16 * wi + lr) * 8), v = lds2f(sb + OFF_X + X_STAT + w * 4096 + (jj * 64 + 16 * wi + lr + 8) * 8);
                    sa.x += u.x; sa.y += u.y; sbb.x += v.x; sbb.y += v.y;
                }
                warp_arrive(BAR(B_EMPTY + 6));
                uint32_t ra2, na2, rb2, nb2;
                ln_coeffs(sa.x * (1.f / DM), sa.y * (1.f / DM), ra2, na2);
                ln_coeffs(sbb.x * (1.f / DM), sbb.y * (1.f / DM), rb2, nb2);
                const uint32_t ha = sb + OFF_Y + w * HALF + (lane >> 4) * 1024 + (2 * wi + ((lane >> 3) & 1)) * 128 + (lane & 7) * 16;
                const uint32_t sta = sb + M_ST + q * 16;
                auto prep = [&](int s, uint32_t* f) {
                    uint32_t x[8];
                    ldsm4(ha + s * 4096, x); ldsm4(ha + s * 4096 + 2048, x + 4);
                    const uint4 st[2] = {lds4(sta + s * 128), lds4(sta + s * 128 + 64)};
#pragma unroll
                    for (int i = 0; i < 2; i++) {
                        f[4 * i] = hfma2(hfma2(x[4 * i], ra2, na2), st[i].x, st[i].y); f[4 * i + 1] = hfma2(hfma2(x[4 * i + 1], rb2, nb2), st[i].x, st[i].y);
                        f[4 * i + 2] = hfma2(hfma2(x[4 * i + 2], ra2, na2), st[i].z, st[i].w); f[4 * i + 3] = hfma2(hfma2(x[4 * i + 3], rb2, nb2), st[i].z, st[i].w);
                    }
                    stsm4(ha + s * 4096, f[0], f[1], f[2], f[3]); stsm4(ha + s * 4096 + 2048, f[4], f[5], f[6], f[7]);
                };
                float ac[128];
                uint32_t fr[3][8];
                const uint64_t bx = mkdesc(sb, DB128);
                reg_def<128>(ac);
                prep(0, fr[0]);
                PROFC(17);
#pragma unroll
                for (int s = 0; s < 14; s++) {
                    const uint32_t* f = fr[s % 3];
                    const uint64_t bd = bx + (slot_off(s % 7) >> 4);
                    WAIT(B_FULL + s % 7, s >= 7);
                    WG_FENCE();
                    wgmma_rs_256<1>(ac, f[0], f[1], f[2], f[3], bd, s != 0);
                    wgmma_rs_256<1>(ac, f[4], f[5], f[6], f[7], bd + 128, 1);
                    WG_COMMIT();
                    if (s < 13) prep(s + 1, fr[(s + 1) % 3]);
                    if (s > 0) { WG_WAIT(1); warp_arrive(BAR(B_EMPTY + (s - 1) % 7)); }
                }
                PROFC(18);
                fence_async_smem();
                WG_WAIT(0);
                reg_fence<128>(ac);
                warp_arrive(BAR(B_EMPTY + 6));
#pragma unroll
                for (int g = 0; g < 16; g++) {
                    h2a[2 * g] = hmul2(pack2_relu(ac[4 * g], ac[4 * g + 1]), pack2(ac[64 + 4 * g], ac[64 + 4 * g + 1]));
                    h2a[2 * g + 1] = hmul2(pack2_relu(ac[4 * g + 2], ac[4 * g + 3]), pack2(ac[64 + 4 * g + 2], ac[64 + 4 * g + 3]));
                    h2g[(fa / 8 + g) * 512] = h2a[2 * g]; h2g[(fa / 8 + g) * 512 + 32] = h2a[2 * g + 1];
                }
                warp_arrive(BAR(B_PUB + 6));
                bar_sync(1 + w, 128);
            }
            PROFC(19);
            {
                float ac[64];
                reg_def<64>(ac);
                const uint64_t bx = mkdesc(sb, dconst(8192, 1024, 1));
#pragma unroll
                for (int s = 0; s < 7; s++) {
                    WAIT(B_FULL + s, 0);
                    const uint64_t ad = a0 + s * 512, bd = bx + (slot_off(s) >> 4);
                    WG_FENCE();
#pragma unroll
                    for (int k = 0; k < 4; k++) wgmma_ss_128<1>(ac, ad + k * 128, bd + k * 128, (s | k) != 0);
                    WG_COMMIT();
                    if (s > 0) { WG_WAIT(1); warp_arrive(BAR(B_EMPTY + s - 1)); }
                }
                WG_WAIT(0);
                reg_fence<64>(ac);
                warp_arrive(BAR(B_EMPTY + 6));
#pragma unroll
                for (int g = 0; g < 8; g++) {
                    h2b[2 * g] = hmul2(pack2_relu(ac[4 * g], ac[4 * g + 1]), pack2(ac[32 + 4 * g], ac[32 + 4 * g + 1]));
                    h2b[2 * g + 1] = hmul2(pack2_relu(ac[4 * g + 2], ac[4 * g + 3]), pack2(ac[32 + 4 * g + 2], ac[32 + 4 * g + 3]));
                    h2g[(fb / 8 + g) * 512] = h2b[2 * g]; h2g[(fb / 8 + g) * 512 + 32] = h2b[2 * g + 1];
                }
                warp_arrive(BAR(B_PUB + 7));
            }
            PROFC(27);
            {
                float ac[32];
                reg_def<32>(ac);
                const uint64_t bx = mkdesc(sb, dconst(4096, 512, 2));
#pragma unroll
                for (int s = 0; s < 7; s++) {
                    WAIT(B_FULL + s, 1);
                    const uint64_t ad = a0 + s * 512, bd = bx + (slot_off(s) >> 4);
                    WG_FENCE();
#pragma unroll
                    for (int k = 0; k < 4; k++) wgmma_ss_64<1>(ac, ad + k * 128, bd + k * 64, (s | k) != 0);
                    WG_COMMIT();
                    if (s > 0) { WG_WAIT(1); warp_arrive(BAR(B_EMPTY + s - 1)); }
                }
                WG_WAIT(0);
                reg_fence<32>(ac);
                __syncwarp();
                if (lane < 6) mbar_arrive(BAR(B_EMPTY + 6 + lane));
                PROFC(20);
#pragma unroll
                for (int g = 0; g < 4; g++) {
                    h2b[16 + 2 * g] = hmul2(pack2_relu(ac[4 * g], ac[4 * g + 1]), pack2(ac[16 + 4 * g], ac[16 + 4 * g + 1]));
                    h2b[16 + 2 * g + 1] = hmul2(pack2_relu(ac[4 * g + 2], ac[4 * g + 3]), pack2(ac[16 + 4 * g + 2], ac[16 + 4 * g + 3]));
                    h2g[(fc / 8 + g) * 512] = h2b[16 + 2 * g]; h2g[(fc / 8 + g) * 512 + 32] = h2b[16 + 2 * g + 1];
                }
                warp_arrive(BAR(B_PUB + 8));
                asm volatile("barrier.cluster.wait.aligned;" ::: "memory");
                if (lane == 0 && !sc) {
                    uint32_t rb;
                    asm volatile("mapa.shared::cluster.u32 %0, %1, %2;" : "=r"(rb) : "r"(BAR(B_PEER)), "r"(kh ^ 1));
                    asm volatile("mbarrier.arrive.relaxed.cluster.shared::cluster.b64 _, [%0];" ::"r"(rb) : "memory");
                }
            }
        } else { reg_def<32>(h2a); reg_def<24>(h2b); }
        PROFC(21);
        if (RUN(7)) {
            float ac[56];
            reg_def<56>(ac);
            constexpr uint64_t DAN = dconst(2048, 128, 0);
            const uint64_t bx = mkdesc(sb, DB128);
#pragma unroll
            for (int e = 0; e < 4; e++) {
                WAIT(B_FULL + e, 0);
                const uint64_t bd = bx + (slot_off(e) >> 4);
                const uint32_t* hh = e < 2 ? h2a + 16 * e : h2b + 16 * (e - 2);
                WG_FENCE();
#pragma unroll
                for (int k = 0; k < (e < 3 ? 4 : 2); k++) wgmma_rs_112<1>(ac, hh[4 * k], hh[4 * k + 1], hh[4 * k + 2], hh[4 * k + 3], bd + (k >> 1) * 512 + (k & 1) * 128, (e | k) != 0);
                WG_COMMIT();
                if (e > 0) { WG_WAIT(1); warp_arrive(BAR(B_EMPTY + e - 1)); }
            }
            PROFC(22);
            const uint64_t ax = mkdesc(sb + 8192 + w * 1024, DAN);
#pragma unroll
            for (int e = 4; e < 25; e++) {
                WAIT(B_FULL + e % 12, e >= 12 && e < 24);
                if (e == 16) PROFC(23);
                const uint64_t ad = ax + (slot_off(e % 12) >> 4), bd = bx + (slot_off(e % 12) >> 4);
                WG_FENCE();
                wgmma_ss_112<1>(ac, ad, bd, 1);
                wgmma_ss_112<1>(ac, ad + 256, bd + 128, 1);
                WG_COMMIT();
                if (e < 14) { WG_WAIT(1); warp_arrive(BAR(B_EMPTY + (e - 1) % 12)); }
            }
            mbar_wait_cluster(BAR(B_PEER), sc);
            WG_WAIT(0);
            reg_fence<56>(ac);
            PROFC(24);
            uint32_t rdst, rbar;
            asm volatile("mapa.shared::cluster.u32 %0, %1, %2;" : "=r"(rdst) : "r"(sb + OFF_Y + (5 + w) * 16384 + t * 16), "r"(kh ^ 1 ^ sc));
            asm volatile("mapa.shared::cluster.u32 %0, %1, %2;" : "=r"(rbar) : "r"(BAR(B_XCH + w)), "r"(kh ^ 1 ^ sc));
#define ACG(g, i) ac[4 * (((g) + 8) % 14) + (i)]
#pragma unroll
            for (int g = 0; g < 7; g++) {
                const float v0 = kh ? ACG(g, 0) : ACG(g + 7, 0), v1 = kh ? ACG(g, 1) : ACG(g + 7, 1);
                const float v2 = kh ? ACG(g, 2) : ACG(g + 7, 2), v3 = kh ? ACG(g, 3) : ACG(g + 7, 3);
                if (!sc) asm volatile("st.async.shared::cluster.mbarrier::complete_tx::bytes.v4.f32 [%0], {%1,%2,%3,%4}, [%5];"
                             ::"r"(rdst + g * 2048), "f"(v0), "f"(v1), "f"(v2), "f"(v3), "r"(rbar) : "memory");
            }
            mbar_wait_cluster(BAR(B_XCH + w), sc);
            PROFC(25);
            bf16* og = (sc ? (bf16*)(g_h2 + 16 * 224 * 512) : p.out + (size_t)128 * r * DM) + (size_t)ra * DM + 56 * j + 2 * q;
#pragma unroll
            for (int g = 0; g < 7; g++) {
                const uint4 rv = *(const uint4*)(smem + OFF_Y + (5 + w) * 16384 + t * 16 + g * 2048);
                const float2 gb = *(const float2*)(smem + M_G + 224 + (8 * g + 2 * q) * 4);
                const float v0 = (kh ? ACG(g + 7, 0) : ACG(g, 0)) + __uint_as_float(rv.x), v1 = (kh ? ACG(g + 7, 1) : ACG(g, 1)) + __uint_as_float(rv.y);
                const float v2 = (kh ? ACG(g + 7, 2) : ACG(g, 2)) + __uint_as_float(rv.z), v3 = (kh ? ACG(g + 7, 3) : ACG(g, 3)) + __uint_as_float(rv.w);
                *(uint32_t*)(og + 8 * g) = pack2(fmaf(gb.x, v0, bf_lo(x1p[2 * g])), fmaf(gb.y, v1, bf_hi(x1p[2 * g])));
                *(uint32_t*)(og + 8 * DM + 8 * g) = pack2(fmaf(gb.x, v2, bf_lo(x1p[2 * g + 1])), fmaf(gb.y, v3, bf_hi(x1p[2 * g + 1])));
            }
        }
        PROFC(26);
        bar_sync(1 + w, 128);
        if (wi == 0) warp_arrive(BAR(B_DONE));
    } else {
        const int lane = fresh_tid() & 31;
        const bool early = kh == 0, gemv = r < 14;
        const int mcol = early ? 16 * (4 * r + nq) : 2 * DM + 32 * (4 * r + nq);
        const uint32_t wmbuf = sb + OFF_Y + HALF;
        asm volatile("setmaxnreg.dec.sync.aligned.u32 56;");
        if (warp == 9) {
#pragma unroll
            for (int i = 56; i < 64; i++) init_e(BAR(i), 1);
            fence_async_smem();
        }
        if (warp == 8) { init_e(BAR(B_WMFULL), 2); fence_async_smem(); }
        bar_arrive(0, 384);
        asm volatile("barrier.cluster.arrive.relaxed.aligned;" ::: "memory");
        uint32_t target = 0;
        if (warp == 8) {
            if (!sc) {
                expect_e(BAR(B_WMFULL), gemv ? 28672 >> early : 0);
                if (early && gemv) { tma3_e(wmbuf, &p.wm, mcol, 0, 0, BAR(B_WMFULL)); tma3_e(wmbuf + 7168, &p.wm, mcol, 224, 0, BAR(B_WMFULL)); }
#pragma unroll 1
                for (int kb = 0; kb < 7; kb++) {
                    expect_e(BAR(B_XFULL + kb), 16384);
                    tma3_e(sb + OFF_X + kb * 16384, &p.xm, 64 * kb, 128 * r, 0, BAR(B_XFULL + kb));
                }
            }
#pragma unroll 1
            for (int mt = 0; mt < 4; mt++) {
                if (mt == 1) {
                    if (!early && gemv) {
#pragma unroll 1
                        for (int k = 0; k < 4; k++) tma3_e(wmbuf + k * 7168, &p.wm, mcol + (k >> 1) * 16, (k & 1) * 224, 0, BAR(B_WMFULL));
                    }
                    bar_sync(9, 384);
                    if (sc) return;
                    mbar_wait(BAR(B_MOD1), 0);
                    mbar_wait(BAR(B_WMFREE), 0);
                }
                if (mt == 2) mbar_wait(BAR(B_XFREE), 0);
                if (mt == 3) mbar_wait(BAR(B_VRFULL), 0);
                const uint32_t bar = BAR(mt == 3 ? B_WOFULL : B_FULLK + mt), dst = sb + (mt < 2 ? OFF_Y : OFF_X) + (mt & 1) * HALF;
                const int c0 = (mt < 2 ? DM + DM * mt : 0) + 56 * j - 8 * kh;
                if (!sc) {
                    expect_e(bar, HALF);
                    tma3_e(dst, mt == 3 ? &p.wo : &p.qkv, c0, 0, 0, bar);
                    tma3_e(dst + HALF / 2, mt == 3 ? &p.wo : &p.qkv, c0, 224, 0, bar);
                }
            }
            expect_e(BAR(B_XCH), 14336);
            expect_e(BAR(B_XCH + 1), 14336);
        } else {
            if (warp == 10 && !sc) {
                l2_prefetch_e((const char*)p.wqkv + (size_t)b * 9408, 9408);
                if (lane == 0) sts1(sb + M_EPOCH, atomicAdd(&g_ticket, 1u) / NCTA);
            }
            if (warp == 11) {
#pragma unroll
                for (int i = 0; i < 8; i++) {
                    const int wd = lane + 32 * i;
                    const uint32_t cb = i < 7 ? __ldg((const uint32_t*)p.c + wd) : 0u;
                    sts1(wmbuf + 28672 + (wd >> 3) * 32 + (wd & 3) * 8 + (wd & 4), pack2(silu_bf(cb & 0xFFFFu), silu_bf(cb >> 16)));
                }
            }
            bar_sync(9, 384);
            if (sc) return;
            target = lds1(sb + M_EPOCH) + 1;
            const uint32_t tag = target & 0xFFFFu;
            if (warp == 11) {
                warp_arrive(BAR(B_WMFULL));
                mbar_wait(BAR(B_GEMV), 0);
                float sum = 0.f;
#pragma unroll
                for (int i = 0; i < 8; i++) sum += *(const float*)(smem + OFF_Y + HALF + 29696 + (i * 32 + (early ? lane & 15 : lane)) * 4);
                const uint32_t word = (pack2(sum, 0.f) << 16) | tag;
                if (gemv) {
                    uint32_t* mg = g_mod + mcol + (early ? (lane & 15) + (lane >> 4) * 4 * 6 * DM : lane);
#pragma unroll
                    for (int i = 0; i < 8; i++) if (i < 4 || !early) st_relaxed(mg + i * 6 * DM, word);
                }
                warp_arrive(BAR(B_WMFREE));
            }
            const uint4* modp = (const uint4*)g_mod + (r & 7) * (6 * DM / 4);
            const bool p2 = warp == 11;
            mbar_wait(BAR(p2 ? B_PUB : B_XFULL + 4), 0);
#pragma unroll 1
            for (int it = p2 ? 0 : warp - 9; it < (p2 ? 2 : warp - 8); it++) {
                const int i0 = lane + 32 * it, imax = p2 ? 251 : 223;
                uint4 v[4];
#pragma unroll 1
                for (int n = 0;; n++) {
                    uint32_t bad = 0;
#pragma unroll
                    for (int k = 0; k < 4; k++) {
                        const int i = min(i0 + 64 * k, imax);
                        v[k] = ld_relaxed4(modp + (i < 224 ? (p2 ? 336 : 0) + i : (i < 238 ? 14 * j + i : 14 * j + i + 322)));
                        bad |= (v[k].x ^ tag) | (v[k].y ^ tag) | (v[k].z ^ tag) | (v[k].w ^ tag);
                    }
                    if (!__any_sync(~0u, bad & 0xFFFFu)) break;
                    if (n > SPIN_LIMIT) __trap();
                }
#pragma unroll
                for (int k = 0; k < 4; k++) {
                    const int i = min(i0 + 64 * k, imax);
                    if (i < 224) {
                        const int isc = i >= 112, c4 = i - 112 * isc;
                        const float one = isc ? 1.f : 0.f;
                        const uint32_t a = sb + M_ST + (c4 >> 2) * 64 + (c4 & 1) * 32 + (c4 & 2) * 4 + (isc ? 0 : 4);
                        sts1(a, pack2(bf_hi(v[k].x) + one, bf_hi(v[k].y) + one));
                        sts1(a + 16, pack2(bf_hi(v[k].z) + one, bf_hi(v[k].w) + one));
                    } else {
                        sts4(sb + M_G + (i - 224) * 16, make_uint4(v[k].x & 0xFFFF0000u, v[k].y & 0xFFFF0000u, v[k].z & 0xFFFF0000u, v[k].w & 0xFFFF0000u));
                    }
                }
                warp_arrive(BAR(p2 ? B_MOD2 : B_MOD1));
            }
            if (warp == 9) {
#pragma unroll 1
                for (int kv = 0; kv < 2; kv++) {
                    mbar_wait(BAR(B_PUB + kv), 0);
                    if (lane >= 1 && lane <= 2 && r >= lane) wait_flag(g_flag + kv * 128 + b - 8 * lane, target);
                    __syncwarp();
                    fence_async_global();
                    const uint32_t dst = sb + OFF_Y + (kv ? Y_VR : Y_K);
                    expect_e(BAR(B_KRFULL + kv), r >= 2 ? 28672 : r == 1 ? 14336 : 0);
                    if (r >= 2) bulk_e(dst, g_kv + (size_t)((b - 16) * 2 + kv) * 3584, 14336, BAR(B_KRFULL + kv));
                    if (r >= 1) bulk_e(dst + 14336, g_kv + (size_t)((b - 8) * 2 + kv) * 3584, 14336, BAR(B_KRFULL + kv));
                }
            } else if (warp == 11) {
                mbar_wait(BAR(B_VRFULL), 0);
                l2_prefetch_e((const char*)p.wg + (size_t)b * 12544, 12544);
                l2_prefetch_e((const char*)p.wu + (size_t)b * 12544, 12544);
                l2_prefetch_e((const char*)p.wd + (size_t)b * 12544, 12544);
            }
        }
        if (warp == 8 || warp == 11) {
            const int sec = warp == 11;
            if (sec) ring_loader<1>(p, sb, r, j); else ring_loader<0>(p, sb, r, j);
            mbar_wait(BAR(B_DONE), 0);
        } else if (warp == 9) {
#pragma unroll
            for (int ev = 0; ev < 4; ev++) expect_e(BAR(B_GFULL + ev), ev < 2 ? HALF : HALF + 4096);
            mbar_wait(BAR(B_PUB + 2), 0);
            const uint32_t* fp = g_flag + (2 + (lane >> 3)) * 128 + 8 * r + (lane & 7);
            const uint32_t* src = g_ox + (size_t)2 * r * 14336;
            const float2* ssrc = g_st + 2 * r * 512;
#pragma unroll 1
            for (int n = 0, ev = 0; ev < 4; n++) {
                if (ev == 1) mbar_wait(BAR(B_PUB + 3), 0);
                uint32_t ok = __ballot_sync(~0u, (int)(ld_relaxed(fp) - target) >= 0) >> (8 * ev);
                while ((ok & 0xFFu) == 0xFFu) {
                    asm volatile("fence.acquire.gpu;" ::: "memory");
                    fence_async_global();
                    const uint32_t bar = BAR(B_GFULL + ev);
                    bulk_e(sb + (ev == 0 ? OFF_X : OFF_Y + (ev & 1) * HALF), src + (ev >> 1) * (34 * 14336) + (ev & 1) * 14336, HALF, bar);
                    if (ev >= 2) bulk_e(sb + OFF_X + X_STAT + (ev & 1) * 4096, ssrc + (ev & 1) * 512, 4096, bar);
                    if (ev) PROFH(4 + ev);
                    ev++; ok >>= 8;
                }
                if (n > SPIN_LIMIT) __trap();
            }
#pragma unroll 1
            for (int ps = 0; ps < 3; ps++) {
                mbar_wait(BAR(B_PUB + 6 + ps), 0);
                if (lane < 4) wait_flag(g_flag + (6 + ps) * 128 + 8 * r + 2 * lane + kh, target);
                warp_arrive(BAR(B_HRDY + ps));
                PROFH(9 + ps);
            }
        } else {
            if (lane == 0) {
#pragma unroll 1
                for (int k = 0; k < 9; k++) {
                    mbar_wait(BAR(B_PUB + k), 0);
                    fence_gpu();
                    st_relaxed(g_flag + k * 128 + b, target);
                    if (k >= 3 && k <= 5) PROFH1(k - 3);
                }
            }
        }
    }
}

typedef CUresult (*EncodeFn)(CUtensorMap*, CUtensorMapDataType, cuuint32_t, void*, const cuuint64_t*, const cuuint64_t*, const cuuint32_t*,
                             const cuuint32_t*, CUtensorMapInterleave, CUtensorMapSwizzle, CUtensorMapL2promotion, CUtensorMapFloatOOBfill);

static void make_map(EncodeFn fn, CUtensorMap* m, const void* ptr, uint64_t d0, uint64_t d1, uint64_t d2, uint64_t s1, uint64_t s2,
                     uint32_t b0, uint32_t b1, uint32_t b2, CUtensorMapSwizzle sw) {
    cuuint64_t dims[3] = {d0, d1, d2}, strides[2] = {s1, s2};
    cuuint32_t box[3] = {b0, b1, b2}, es[3] = {1, 1, 1};
    CUresult rc = fn(m, CU_TENSOR_MAP_DATA_TYPE_BFLOAT16, 3, (void*)ptr, dims, strides, box, es, CU_TENSOR_MAP_INTERLEAVE_NONE, sw,
                     CU_TENSOR_MAP_L2_PROMOTION_L2_128B, CU_TENSOR_MAP_FLOAT_OOB_FILL_NONE);
    (void)rc;
}

extern "C" void kernel_launch(void* const* d_in, const int* in_sizes, int n_in, void* d_out, int out_size) {
    (void)in_sizes; (void)n_in; (void)out_size;
    static EncodeFn fn = nullptr;
    if (!fn) {
        cudaDriverEntryPointQueryResult st;
        cudaGetDriverEntryPoint("cuTensorMapEncodeTiled", (void**)&fn, cudaEnableDefault, &st);
        cudaFuncSetAttribute(fused_block_kernel, cudaFuncAttributeMaxDynamicSharedMemorySize, SMEM_BYTES);
    }
    Params p;
    p.x = (const bf16*)d_in[0];
    const bf16* wqkv = (const bf16*)d_in[1];
    p.wqkv = wqkv;
    p.wop = (const bf16*)d_in[2];
    p.wg = (const bf16*)d_in[4];
    p.wu = (const bf16*)d_in[5];
    p.wd = (const bf16*)d_in[6];
    p.c = (const bf16*)d_in[7];
    p.wmod = (const bf16*)d_in[8];
    p.out = (bf16*)d_out;
    p.zero = 0;
    make_map(fn, &p.wm, p.wmod, 2688, 448, 1, 5376, 5376 * 448, 16, 224, 1, CU_TENSOR_MAP_SWIZZLE_NONE);
    make_map(fn, &p.xm, p.x, 448, 2048, 1, 896, 896 * 2048, 64, 128, 1, CU_TENSOR_MAP_SWIZZLE_128B);
    make_map(fn, &p.qkv, wqkv, 1344, 448, 1, 2688, 2688 * 448, 64, 224, 1, CU_TENSOR_MAP_SWIZZLE_128B);
    make_map(fn, &p.wo, p.wop, 448, 448, 1, 896, 896 * 448, 64, 224, 1, CU_TENSOR_MAP_SWIZZLE_128B);
    make_map(fn, &p.ga, p.wg, 64, 448, 28, 3584, 128, 64, 32, 2, CU_TENSOR_MAP_SWIZZLE_128B);
    make_map(fn, &p.ua, p.wu, 64, 448, 28, 3584, 128, 64, 32, 2, CU_TENSOR_MAP_SWIZZLE_128B);
    make_map(fn, &p.gb, p.wg, 64, 448, 28, 3584, 128, 64, 64, 1, CU_TENSOR_MAP_SWIZZLE_128B);
    make_map(fn, &p.ub, p.wu, 64, 448, 28, 3584, 128, 64, 64, 1, CU_TENSOR_MAP_SWIZZLE_128B);
    make_map(fn, &p.gc, p.wg, 32, 448, 56, 3584, 64, 32, 64, 1, CU_TENSOR_MAP_SWIZZLE_64B);
    make_map(fn, &p.uc, p.wu, 32, 448, 56, 3584, 64, 32, 64, 1, CU_TENSOR_MAP_SWIZZLE_64B);
    make_map(fn, &p.dn, p.wd, 448, 1792, 1, 896, 896 * 1792, 64, 32, 1, CU_TENSOR_MAP_SWIZZLE_128B);
    fused_block_kernel<<<GRID, 384, SMEM_BYTES>>>(p);
}
```

```cpp
#include <cuda_runtime.h>
#include <cuda_bf16.h>
#include <cuda.h>
#include <stdint.h>

typedef __nv_bfloat16 bf16;

template<int TB> __device__ __forceinline__ void wgmma_rs_56(float* d, uint32_t a0, uint32_t a1, uint32_t a2, uint32_t a3, uint64_t db, int sd) {
  asm volatile("{\n.reg .pred p;\nsetp.ne.b32 p, %33, 0;\n"
    "wgmma.mma_async.sync.aligned.m64n56k16.f32.bf16.bf16 {%0,%1,%2,%3,%4,%5,%6,%7,%8,%9,%10,%11,%12,%13,%14,%15,%16,%17,%18,%19,%20,%21,%22,%23,%24,%25,%26,%27}, {%28,%29,%30,%31}, %32, p, 1, 1, %34;\n}\n"
    : "+f"(d[0]),"+f"(d[1]),"+f"(d[2]),"+f"(d[3]),"+f"(d[4]),"+f"(d[5]),"+f"(d[6]),"+f"(d[7]),"+f"(d[8]),"+f"(d[9]),"+f"(d[10]),"+f"(d[11]),"+f"(d[12]),"+f"(d[13]),"+f"(d[14]),"+f"(d[15]),"+f"(d[16]),"+f"(d[17]),"+f"(d[18]),"+f"(d[19]),"+f"(d[20]),"+f"(d[21]),"+f"(d[22]),"+f"(d[23]),"+f"(d[24]),"+f"(d[25]),"+f"(d[26]),"+f"(d[27])
    : "r"(a0), "r"(a1), "r"(a2), "r"(a3), "l"(db), "r"(sd), "n"(TB));
}
template<int TB> __device__ __forceinline__ void wgmma_ss_56(float* d, uint64_t da, uint64_t db, int sd) {
  asm volatile("{\n.reg .pred p;\nsetp.ne.b32 p, %30, 0;\n"
    "wgmma.mma_async.sync.aligned.m64n56k16.f32.bf16.bf16 {%0,%1,%2,%3,%4,%5,%6,%7,%8,%9,%10,%11,%12,%13,%14,%15,%16,%17,%18,%19,%20,%21,%22,%23,%24,%25,%26,%27}, %28, %29, p, 1, 1, 0, %31;\n}\n"
    : "+f"(d[0]),"+f"(d[1]),"+f"(d[2]),"+f"(d[3]),"+f"(d[4]),"+f"(d[5]),"+f"(d[6]),"+f"(d[7]),"+f"(d[8]),"+f"(d[9]),"+f"(d[10]),"+f"(d[11]),"+f"(d[12]),"+f"(d[13]),"+f"(d[14]),"+f"(d[15]),"+f"(d[16]),"+f"(d[17]),"+f"(d[18]),"+f"(d[19]),"+f"(d[20]),"+f"(d[21]),"+f"(d[22]),"+f"(d[23]),"+f"(d[24]),"+f"(d[25]),"+f"(d[26]),"+f"(d[27])
    : "l"(da), "l"(db), "r"(sd), "n"(TB));
}
template<int TB> __device__ __forceinline__ void wgmma_rs_256(float* d, uint32_t a0, uint32_t a1, uint32_t a2, uint32_t a3, uint64_t db, int sd) {
  asm volatile("{\n.reg .pred p;\nsetp.ne.b32 p, %133, 0;\n"
    "wgmma.mma_async.sync.aligned.m64n256k16.f32.bf16.bf16 {%0,%1,%2,%3,%4,%5,%6,%7,%8,%9,%10,%11,%12,%13,%14,%15,%16,%17,%18,%19,%20,%21,%22,%23,%24,%25,%26,%27,%28,%29,%30,%31,%32,%33,%34,%35,%36,%37,%38,%39,%40,%41,%42,%43,%44,%45,%46,%47,%48,%49,%50,%51,%52,%53,%54,%55,%56,%57,%58,%59,%60,%61,%62,%63,%64,%65,%66,%67,%68,%69,%70,%71,%72,%73,%74,%75,%76,%77,%78,%79,%80,%81,%82,%83,%84,%85,%86,%87,%88,%89,%90,%91,%92,%93,%94,%95,%96,%97,%98,%99,%100,%101,%102,%103,%104,%105,%106,%107,%108,%109,%110,%111,%112,%113,%114,%115,%116,%117,%118,%119,%120,%121,%122,%123,%124,%125,%126,%127}, {%128,%129,%130,%131}, %132, p, 1, 1, %134;\n}\n"
    : "+f"(d[0]),"+f"(d[1]),"+f"(d[2]),"+f"(d[3]),"+f"(d[4]),"+f"(d[5]),"+f"(d[6]),"+f"(d[7]),"+f"(d[8]),"+f"(d[9]),"+f"(d[10]),"+f"(d[11]),"+f"(d[12]),"+f"(d[13]),"+f"(d[14]),"+f"(d[15]),"+f"(d[16]),"+f"(d[17]),"+f"(d[18]),"+f"(d[19]),"+f"(d[20]),"+f"(d[21]),"+f"(d[22]),"+f"(d[23]),"+f"(d[24]),"+f"(d[25]),"+f"(d[26]),"+f"(d[27]),"+f"(d[28]),"+f"(d[29]),"+f"(d[30]),"+f"(d[31]),"+f"(d[32]),"+f"(d[33]),"+f"(d[34]),"+f"(d[35]),"+f"(d[36]),"+f"(d[37]),"+f"(d[38]),"+f"(d[39]),"+f"(d[40]),"+f"(d[41]),"+f"(d[42]),"+f"(d[43]),"+f"(d[44]),"+f"(d[45]),"+f"(d[46]),"+f"(d[47]),"+f"(d[48]),"+f"(d[49]),"+f"(d[50]),"+f"(d[51]),"+f"(d[52]),"+f"(d[53]),"+f"(d[54]),"+f"(d[55]),"+f"(d[56]),"+f"(d[57]),"+f"(d[58]),"+f"(d[59]),"+f"(d[60]),"+f"(d[61]),"+f"(d[62]),"+f"(d[63]),"+f"(d[64]),"+f"(d[65]),"+f"(d[66]),"+f"(d[67]),"+f"(d[68]),"+f"(d[69]),"+f"(d[70]),"+f"(d[71]),"+f"(d[72]),"+f"(d[73]),"+f"(d[74]),"+f"(d[75]),"+f"(d[76]),"+f"(d[77]),"+f"(d[78]),"+f"(d[79]),"+f"(d[80]),"+f"(d[81]),"+f"(d[82]),"+f"(d[83]),"+f"(d[84]),"+f"(d[85]),"+f"(d[86]),"+f"(d[87]),"+f"(d[88]),"+f"(d[89]),"+f"(d[90]),"+f"(d[91]),"+f"(d[92]),"+f"(d[93]),"+f"(d[94]),"+f"(d[95]),"+f"(d[96]),"+f"(d[97]),"+f"(d[98]),"+f"(d[99]),"+f"(d[100]),"+f"(d[101]),"+f"(d[102]),"+f"(d[103]),"+f"(d[104]),"+f"(d[105]),"+f"(d[106]),"+f"(d[107]),"+f"(d[108]),"+f"(d[109]),"+f"(d[110]),"+f"(d[111]),"+f"(d[112]),"+f"(d[113]),"+f"(d[114]),"+f"(d[115]),"+f"(d[116]),"+f"(d[117]),"+f"(d[118]),"+f"(d[119]),"+f"(d[120]),"+f"(d[121]),"+f"(d[122]),"+f"(d[123]),"+f"(d[124]),"+f"(d[125]),"+f"(d[126]),"+f"(d[127])
    : "r"(a0), "r"(a1), "r"(a2), "r"(a3), "l"(db), "r"(sd), "n"(TB));
}
template<int TB> __device__ __forceinline__ void wgmma_ss_128(float* d, uint64_t da, uint64_t db, int sd) {
  asm volatile("{\n.reg .pred p;\nsetp.ne.b32 p, %66, 0;\n"
    "wgmma.mma_async.sync.aligned.m64n128k16.f32.bf16.bf16 {%0,%1,%2,%3,%4,%5,%6,%7,%8,%9,%10,%11,%12,%13,%14,%15,%16,%17,%18,%19,%20,%21,%22,%23,%24,%25,%26,%27,%28,%29,%30,%31,%32,%33,%34,%35,%36,%37,%38,%39,%40,%41,%42,%43,%44,%45,%46,%47,%48,%49,%50,%51,%52,%53,%54,%55,%56,%57,%58,%59,%60,%61,%62,%63}, %64, %65, p, 1, 1, 0, %67;\n}\n"
    : "+f"(d[0]),"+f"(d[1]),"+f"(d[2]),"+f"(d[3]),"+f"(d[4]),"+f"(d[5]),"+f"(d[6]),"+f"(d[7]),"+f"(d[8]),"+f"(d[9]),"+f"(d[10]),"+f"(d[11]),"+f"(d[12]),"+f"(d[13]),"+f"(d[14]),"+f"(d[15]),"+f"(d[16]),"+f"(d[17]),"+f"(d[18]),"+f"(d[19]),"+f"(d[20]),"+f"(d[21]),"+f"(d[22]),"+f"(d[23]),"+f"(d[24]),"+f"(d[25]),"+f"(d[26]),"+f"(d[27]),"+f"(d[28]),"+f"(d[29]),"+f"(d[30]),"+f"(d[31]),"+f"(d[32]),"+f"(d[33]),"+f"(d[34]),"+f"(d[35]),"+f"(d[36]),"+f"(d[37]),"+f"(d[38]),"+f"(d[39]),"+f"(d[40]),"+f"(d[41]),"+f"(d[42]),"+f"(d[43]),"+f"(d[44]),"+f"(d[45]),"+f"(d[46]),"+f"(d[47]),"+f"(d[48]),"+f"(d[49]),"+f"(d[50]),"+f"(d[51]),"+f"(d[52]),"+f"(d[53]),"+f"(d[54]),"+f"(d[55]),"+f"(d[56]),"+f"(d[57]),"+f"(d[58]),"+f"(d[59]),"+f"(d[60]),"+f"(d[61]),"+f"(d[62]),"+f"(d[63])
    : "l"(da), "l"(db), "r"(sd), "n"(TB));
}
template<int TB> __device__ __forceinline__ void wgmma_ss_64(float* d, uint64_t da, uint64_t db, int sd) {
  asm volatile("{\n.reg .pred p;\nsetp.ne.b32 p, %34, 0;\n"
    "wgmma.mma_async.sync.aligned.m64n64k16.f32.bf16.bf16 {%0,%1,%2,%3,%4,%5,%6,%7,%8,%9,%10,%11,%12,%13,%14,%15,%16,%17,%18,%19,%20,%21,%22,%23,%24,%25,%26,%27,%28,%29,%30,%31}, %32, %33, p, 1, 1, 0, %35;\n}\n"
    : "+f"(d[0]),"+f"(d[1]),"+f"(d[2]),"+f"(d[3]),"+f"(d[4]),"+f"(d[5]),"+f"(d[6]),"+f"(d[7]),"+f"(d[8]),"+f"(d[9]),"+f"(d[10]),"+f"(d[11]),"+f"(d[12]),"+f"(d[13]),"+f"(d[14]),"+f"(d[15]),"+f"(d[16]),"+f"(d[17]),"+f"(d[18]),"+f"(d[19]),"+f"(d[20]),"+f"(d[21]),"+f"(d[22]),"+f"(d[23]),"+f"(d[24]),"+f"(d[25]),"+f"(d[26]),"+f"(d[27]),"+f"(d[28]),"+f"(d[29]),"+f"(d[30]),"+f"(d[31])
    : "l"(da), "l"(db), "r"(sd), "n"(TB));
}
template<int TB> __device__ __forceinline__ void wgmma_ss_112(float* d, uint64_t da, uint64_t db, int sd) {
  asm volatile("{\n.reg .pred p;\nsetp.ne.b32 p, %58, 0;\n"
    "wgmma.mma_async.sync.aligned.m64n112k16.f32.bf16.bf16 {%0,%1,%2,%3,%4,%5,%6,%7,%8,%9,%10,%11,%12,%13,%14,%15,%16,%17,%18,%19,%20,%21,%22,%23,%24,%25,%26,%27,%28,%29,%30,%31,%32,%33,%34,%35,%36,%37,%38,%39,%40,%41,%42,%43,%44,%45,%46,%47,%48,%49,%50,%51,%52,%53,%54,%55}, %56, %57, p, 1, 1, 0, %59;\n}\n"
    : "+f"(d[0]),"+f"(d[1]),"+f"(d[2]),"+f"(d[3]),"+f"(d[4]),"+f"(d[5]),"+f"(d[6]),"+f"(d[7]),"+f"(d[8]),"+f"(d[9]),"+f"(d[10]),"+f"(d[11]),"+f"(d[12]),"+f"(d[13]),"+f"(d[14]),"+f"(d[15]),"+f"(d[16]),"+f"(d[17]),"+f"(d[18]),"+f"(d[19]),"+f"(d[20]),"+f"(d[21]),"+f"(d[22]),"+f"(d[23]),"+f"(d[24]),"+f"(d[25]),"+f"(d[26]),"+f"(d[27]),"+f"(d[28]),"+f"(d[29]),"+f"(d[30]),"+f"(d[31]),"+f"(d[32]),"+f"(d[33]),"+f"(d[34]),"+f"(d[35]),"+f"(d[36]),"+f"(d[37]),"+f"(d[38]),"+f"(d[39]),"+f"(d[40]),"+f"(d[41]),"+f"(d[42]),"+f"(d[43]),"+f"(d[44]),"+f"(d[45]),"+f"(d[46]),"+f"(d[47]),"+f"(d[48]),"+f"(d[49]),"+f"(d[50]),"+f"(d[51]),"+f"(d[52]),"+f"(d[53]),"+f"(d[54]),"+f"(d[55])
    : "l"(da), "l"(db), "r"(sd), "n"(TB));
}
template<int TB> __device__ __forceinline__ void wgmma_rs_112(float* d, uint32_t a0, uint32_t a1, uint32_t a2, uint32_t a3, uint64_t db, int sd) {
  asm volatile("{\n.reg .pred p;\nsetp.ne.b32 p, %61, 0;\n"
    "wgmma.mma_async.sync.aligned.m64n112k16.f32.bf16.bf16 {%0,%1,%2,%3,%4,%5,%6,%7,%8,%9,%10,%11,%12,%13,%14,%15,%16,%17,%18,%19,%20,%21,%22,%23,%24,%25,%26,%27,%28,%29,%30,%31,%32,%33,%34,%35,%36,%37,%38,%39,%40,%41,%42,%43,%44,%45,%46,%47,%48,%49,%50,%51,%52,%53,%54,%55}, {%56,%57,%58,%59}, %60, p, 1, 1, %62;\n}\n"
    : "+f"(d[0]),"+f"(d[1]),"+f"(d[2]),"+f"(d[3]),"+f"(d[4]),"+f"(d[5]),"+f"(d[6]),"+f"(d[7]),"+f"(d[8]),"+f"(d[9]),"+f"(d[10]),"+f"(d[11]),"+f"(d[12]),"+f"(d[13]),"+f"(d[14]),"+f"(d[15]),"+f"(d[16]),"+f"(d[17]),"+f"(d[18]),"+f"(d[19]),"+f"(d[20]),"+f"(d[21]),"+f"(d[22]),"+f"(d[23]),"+f"(d[24]),"+f"(d[25]),"+f"(d[26]),"+f"(d[27]),"+f"(d[28]),"+f"(d[29]),"+f"(d[30]),"+f"(d[31]),"+f"(d[32]),"+f"(d[33]),"+f"(d[34]),"+f"(d[35]),"+f"(d[36]),"+f"(d[37]),"+f"(d[38]),"+f"(d[39]),"+f"(d[40]),"+f"(d[41]),"+f"(d[42]),"+f"(d[43]),"+f"(d[44]),"+f"(d[45]),"+f"(d[46]),"+f"(d[47]),"+f"(d[48]),"+f"(d[49]),"+f"(d[50]),"+f"(d[51]),"+f"(d[52]),"+f"(d[53]),"+f"(d[54]),"+f"(d[55])
    : "r"(a0), "r"(a1), "r"(a2), "r"(a3), "l"(db), "r"(sd), "n"(TB));
}

constexpr int DM = 448;
constexpr int NCTA = 128;
#define MAPPING 1
#define GRID 132
#define PINGPONG 0
#define WIN 4
#define WIN_END 25
#define UNR_G2 21
#define UNR_B 7
#define UNR_C 7
constexpr int kG2 = UNR_G2, kB = UNR_B, kC = UNR_C;
#define MAP_S 4
constexpr int SPIN_LIMIT = 1 << 22;

constexpr uint32_t OFF_X = 0, OFF_Y = 114688, OFF_MISC = 229376, SMEM_BYTES = 232448;
constexpr uint32_t Y_VR = 0, Y_K = 28672, Y_KOWN = 57344, Y_VOWN = 71680, Y_Q = 86016;
constexpr uint32_t HALF = 57344;
constexpr uint32_t M_BAR = OFF_MISC;
constexpr uint32_t M_ST = OFF_MISC + 512;
constexpr uint32_t M_G = OFF_MISC + 2304;
constexpr uint32_t M_EPOCH = OFF_MISC + 3040;
enum { B_XFULL = 0, B_FULLK = 7, B_FULLV = 8, B_FULLQ, B_KRFULL, B_VRFULL, B_WOFULL, B_XCH, B_FULL = 16, B_MOD1 = 28, B_MOD2, B_WMFULL,
       B_EMPTY = 32, B_XFREE = B_EMPTY + 12, B_GEMV, B_PEER,
       B_PUB = 47,
       B_WMFREE = 56, B_HRDY, B_GFULL = B_HRDY + 3, B_DONE = 31 };
constexpr uint32_t X_STAT = 49152;

__device__ uint32_t g_ticket;
__device__ __align__(128) uint32_t g_mod[8 * 6 * DM];
__device__ __align__(128) uint32_t g_flag[9 * 16 * 8];
__device__ __align__(128) uint32_t g_kv[17 * 8 * 2 * 3584];
__device__ __align__(128) uint32_t g_ox[2 * 34 * 14336];
#define g_o g_ox
#define g_x1 (g_ox + 34 * 14336)
__device__ __align__(128) float2 g_st[34 * 8 * 64];
__device__ __align__(128) uint32_t g_h2[17 * 224 * 512];
#define PROFH(id)
#define PROFH1(id)
#define PROFC(id)

struct alignas(64) Params {
    CUtensorMap wm, xm, qkv, wo, ga, ua, gb, ub, gc, uc, dn;
    const bf16 *x, *c, *wqkv, *wmod, *wg, *wu, *wd, *wop;
    bf16* out;
    uint32_t zero;
};

__device__ __forceinline__ void mbar_init(uint32_t bar, int cnt) { asm volatile("mbarrier.init.shared::cta.b64 [%0], %1;" ::"r"(bar), "r"(cnt) : "memory"); }
__device__ __forceinline__ void mbar_expect_tx(uint32_t bar, uint32_t bytes) { asm volatile("mbarrier.arrive.expect_tx.shared::cta.b64 _, [%0], %1;" ::"r"(bar), "r"(bytes) : "memory"); }
__device__ __forceinline__ void mbar_arrive(uint32_t bar) { asm volatile("mbarrier.arrive.shared::cta.b64 _, [%0];" ::"r"(bar) : "memory"); }
__device__ __forceinline__ void mbar_wait(uint32_t bar, uint32_t parity) {
    uint32_t ok; int n = 0;
    do {
        asm volatile("{\n.reg .pred p;\nmbarrier.try_wait.parity.shared::cta.b64 p, [%1], %2;\nselp.u32 %0, 1, 0, p;\n}" : "=r"(ok) : "r"(bar), "r"(parity) : "memory");
        if (++n > SPIN_LIMIT) __trap();
    } while (!ok);
}
__device__ __forceinline__ void mbar_wait_c(uint32_t bar, uint32_t parity) {
    asm volatile("{\n.reg .pred p;\nWL:\nmbarrier.try_wait.parity.shared::cta.b64 p, [%0], %1;\n@!p bra WL;\n}" ::"r"(bar), "r"(parity) : "memory");
}
__device__ __forceinline__ void mbar_wait_cluster(uint32_t bar, uint32_t parity) {
    uint32_t ok; int n = 0;
    do {
        asm volatile("{\n.reg .pred p;\nmbarrier.try_wait.parity.acquire.cluster.shared::cta.b64 p, [%1], %2;\nselp.u32 %0, 1, 0, p;\n}" : "=r"(ok) : "r"(bar), "r"(parity) : "memory");
        if (++n > SPIN_LIMIT) __trap();
    } while (!ok);
}
__device__ __forceinline__ void warp_arrive(uint32_t bar) {
    __syncwarp();
    asm volatile("{\n.reg .pred p;\nelect.sync _|p, 0xffffffff;\n@p mbarrier.arrive.shared::cta.b64 _, [%0];\n}" ::"r"(bar) : "memory");
}
__device__ __forceinline__ int opaque(int v) { return __shfl_sync(~0u, v, 0); }
__device__ __forceinline__ int fresh_tid() { int v; asm volatile("mov.u32 %0, %%tid.x;" : "=r"(v)); return v; }
__device__ __forceinline__ void bar_sync(int id, int n) { asm volatile("bar.sync %0, %1;" ::"r"(id), "r"(n) : "memory"); }
__device__ __forceinline__ void bar_arrive(int id, int n) { asm volatile("bar.arrive %0, %1;" ::"r"(id), "r"(n) : "memory"); }
__device__ __forceinline__ void fence_async_smem() { asm volatile("fence.proxy.async.shared::cta;" ::: "memory"); }
__device__ __forceinline__ void fence_async_global() { asm volatile("fence.proxy.async.global;" ::: "memory"); }
__device__ __forceinline__ void fence_gpu() { asm volatile("fence.release.gpu;" ::: "memory"); }
__device__ __forceinline__ void tma3(uint32_t dst, const CUtensorMap* m, int c0, int c1, int c2, uint32_t bar) {
    asm volatile("cp.async.bulk.tensor.3d.shared::cluster.global.mbarrier::complete_tx::bytes [%0], [%1, {%3, %4, %5}], [%2];"
                 ::"r"(dst), "l"(m), "r"(bar), "r"(c0), "r"(c1), "r"(c2) : "memory");
}
__device__ __forceinline__ void bulk_load(uint32_t dst, const void* src, uint32_t bytes, uint32_t bar) {
    asm volatile("cp.async.bulk.shared::cluster.global.mbarrier::complete_tx::bytes [%0], [%1], %2, [%3];" ::"r"(dst), "l"(src), "r"(bytes), "r"(bar) : "memory");
}
__device__ __forceinline__ void expect_e(uint32_t bar, uint32_t bytes) {
    asm volatile("{\n.reg .pred p;\nelect.sync _|p, 0xffffffff;\n@p mbarrier.arrive.expect_tx.shared::cta.b64 _, [%0], %1;\n}" ::"r"(bar), "r"(bytes) : "memory");
}
__device__ __forceinline__ void tma3_e(uint32_t dst, const CUtensorMap* m, int c0, int c1, int c2, uint32_t bar) {
    asm volatile("{\n.reg .pred p;\nelect.sync _|p, 0xffffffff;\n@p cp.async.bulk.tensor.3d.shared::cluster.global.mbarrier::complete_tx::bytes [%0], [%1, {%3, %4, %5}], [%2];\n}"
                 ::"r"(dst), "l"(m), "r"(bar), "r"(c0), "r"(c1), "r"(c2) : "memory");
}
__device__ __forceinline__ void bulk_e(uint32_t dst, const void* src, uint32_t bytes, uint32_t bar) {
    asm volatile("{\n.reg .pred p;\nelect.sync _|p, 0xffffffff;\n@p cp.async.bulk.shared::cluster.global.mbarrier::complete_tx::bytes [%0], [%1], %2, [%3];\n}"
                 ::"r"(dst), "l"(src), "r"(bytes), "r"(bar) : "memory");
}
__device__ __forceinline__ void init_e(uint32_t bar, int cnt) {
    asm volatile("{\n.reg .pred p;\nelect.sync _|p, 0xffffffff;\n@p mbarrier.init.shared::cta.b64 [%0], %1;\n}" ::"r"(bar), "r"(cnt) : "memory");
}
__device__ __forceinline__ void l2_prefetch_e(const void* src, uint32_t bytes) {
    asm volatile("{\n.reg .pred p;\nelect.sync _|p, 0xffffffff;\n@p cp.async.bulk.prefetch.L2.global [%0], %1;\n}" ::"l"(src), "r"(bytes) : "memory");
}
__device__ __forceinline__ uint32_t ld_relaxed(const uint32_t* p) { uint32_t v; asm volatile("ld.relaxed.gpu.global.u32 %0, [%1];" : "=r"(v) : "l"(p) : "memory"); return v; }
__device__ __forceinline__ void st_relaxed(uint32_t* p, uint32_t v) { asm volatile("st.relaxed.gpu.global.u32 [%0], %1;" ::"l"(p), "r"(v) : "memory"); }
__device__ __forceinline__ uint4 ld_relaxed4(const uint4* p) { uint4 v; asm volatile("ld.relaxed.gpu.global.v4.u32 {%0,%1,%2,%3}, [%4];" : "=r"(v.x), "=r"(v.y), "=r"(v.z), "=r"(v.w) : "l"(p) : "memory"); return v; }
__device__ __forceinline__ void st_relaxed4(uint4* p, uint4 v) { asm volatile("st.relaxed.gpu.global.v4.u32 [%0], {%1,%2,%3,%4};" ::"l"(p), "r"(v.x), "r"(v.y), "r"(v.z), "r"(v.w) : "memory"); }
__device__ __forceinline__ uint4 ldg_nc4(const void* p) { uint4 v; asm volatile("ld.global.nc.L1::no_allocate.v4.u32 {%0,%1,%2,%3}, [%4];" : "=r"(v.x), "=r"(v.y), "=r"(v.z), "=r"(v.w) : "l"(p)); return v; }
__device__ __forceinline__ uint32_t ldg_nc(const void* p) { uint32_t v; asm volatile("ld.global.nc.u32 %0, [%1];" : "=r"(v) : "l"(p)); return v; }
__device__ __forceinline__ uint32_t ld_acquire(const uint32_t* p) { uint32_t v; asm volatile("ld.acquire.gpu.global.u32 %0, [%1];" : "=r"(v) : "l"(p) : "memory"); return v; }
__device__ __forceinline__ uint4 lds4(uint32_t a) { uint4 v; asm volatile("ld.shared.v4.u32 {%0,%1,%2,%3}, [%4];" : "=r"(v.x), "=r"(v.y), "=r"(v.z), "=r"(v.w) : "r"(a) : "memory"); return v; }
__device__ __forceinline__ float2 lds2f(uint32_t a) { float2 v; asm volatile("ld.shared.v2.f32 {%0,%1}, [%2];" : "=f"(v.x), "=f"(v.y) : "r"(a) : "memory"); return v; }
__device__ __forceinline__ uint32_t lds1(uint32_t a) { uint32_t v; asm volatile("ld.shared.u32 %0, [%1];" : "=r"(v) : "r"(a) : "memory"); return v; }
__device__ __forceinline__ void sts4(uint32_t a, uint4 v) { asm volatile("st.shared.v4.u32 [%0], {%1,%2,%3,%4};" ::"r"(a), "r"(v.x), "r"(v.y), "r"(v.z), "r"(v.w) : "memory"); }
__device__ __forceinline__ void sts2(uint32_t a, uint32_t x, uint32_t y) { asm volatile("st.shared.v2.u32 [%0], {%1,%2};" ::"r"(a), "r"(x), "r"(y) : "memory"); }
__device__ __forceinline__ void sts1(uint32_t a, uint32_t v) { asm volatile("st.shared.u32 [%0], %1;" ::"r"(a), "r"(v) : "memory"); }
__device__ __forceinline__ void stsm4(uint32_t a, uint32_t r0, uint32_t r1, uint32_t r2, uint32_t r3) {
    asm volatile("stmatrix.sync.aligned.m8n8.x4.shared.b16 [%0], {%1,%2,%3,%4};" ::"r"(a), "r"(r0), "r"(r1), "r"(r2), "r"(r3));
}
__device__ __forceinline__ uint32_t pack2(float lo, float hi) { uint32_t r; asm("cvt.rn.bf16x2.f32 %0, %1, %2;" : "=r"(r) : "f"(hi), "f"(lo)); return r; }
__device__ __forceinline__ uint32_t pack2_relu(float lo, float hi) { uint32_t r; asm("cvt.rn.relu.bf16x2.f32 %0, %1, %2;" : "=r"(r) : "f"(hi), "f"(lo)); return r; }
__device__ __forceinline__ uint32_t hfma2(uint32_t a, uint32_t b, uint32_t c) { uint32_t r; asm("fma.rn.bf16x2 %0, %1, %2, %3;" : "=r"(r) : "r"(a), "r"(b), "r"(c)); return r; }
__device__ __forceinline__ uint32_t hmul2(uint32_t a, uint32_t b) { uint32_t r; asm("mul.rn.bf16x2 %0, %1, %2;" : "=r"(r) : "r"(a), "r"(b)); return r; }
__device__ __forceinline__ float bf_lo(uint32_t v) { return __uint_as_float(v << 16); }
__device__ __forceinline__ float bf_hi(uint32_t v) { return __uint_as_float(v & 0xFFFF0000u); }
__device__ __forceinline__ float bf_round(float v) { return bf_lo(pack2(v, 0.f)); }
__device__ __forceinline__ float ex2(float x) { float r; asm("ex2.approx.ftz.f32 %0, %1;" : "=f"(r) : "f"(x)); return r; }
__device__ __forceinline__ void mma16816(float* d, uint32_t a0, uint32_t a1, uint32_t a2, uint32_t a3, uint32_t b0, uint32_t b1) {
    asm("mma.sync.aligned.m16n8k16.row.col.f32.bf16.bf16.f32 {%0,%1,%2,%3}, {%4,%5,%6,%7}, {%8,%9}, {%0,%1,%2,%3};"
        : "+f"(d[0]), "+f"(d[1]), "+f"(d[2]), "+f"(d[3]) : "r"(a0), "r"(a1), "r"(a2), "r"(a3), "r"(b0), "r"(b1));
}
__device__ __forceinline__ void mma16816_first(float* d, uint32_t a0, uint32_t a1, uint32_t a2, uint32_t a3, uint32_t b0, uint32_t b1) {
    asm volatile("mma.sync.aligned.m16n8k16.row.col.f32.bf16.bf16.f32 {%0,%1,%2,%3}, {%4,%5,%6,%7}, {%8,%9}, {%10,%10,%10,%10};"
        : "=f"(d[0]), "=f"(d[1]), "=f"(d[2]), "=f"(d[3]) : "r"(a0), "r"(a1), "r"(a2), "r"(a3), "r"(b0), "r"(b1), "f"(0.f));
}
__device__ __forceinline__ void mma16816_v(float* d, uint32_t a0, uint32_t a1, uint32_t a2, uint32_t a3, uint32_t b0, uint32_t b1) {
    asm volatile("mma.sync.aligned.m16n8k16.row.col.f32.bf16.bf16.f32 {%0,%1,%2,%3}, {%4,%5,%6,%7}, {%8,%9}, {%0,%1,%2,%3};"
        : "+f"(d[0]), "+f"(d[1]), "+f"(d[2]), "+f"(d[3]) : "r"(a0), "r"(a1), "r"(a2), "r"(a3), "r"(b0), "r"(b1));
}
__device__ __forceinline__ void mma1688(float* d, uint32_t a0, uint32_t a1, uint32_t b0) {
    asm("mma.sync.aligned.m16n8k8.row.col.f32.bf16.bf16.f32 {%0,%1,%2,%3}, {%4,%5}, {%6}, {%0,%1,%2,%3};"
        : "+f"(d[0]), "+f"(d[1]), "+f"(d[2]), "+f"(d[3]) : "r"(a0), "r"(a1), "r"(b0));
}
__device__ __forceinline__ void ldsm4(uint32_t a, uint32_t* r) {
    asm volatile("ldmatrix.sync.aligned.m8n8.x4.shared.b16 {%0,%1,%2,%3}, [%4];" : "=r"(r[0]), "=r"(r[1]), "=r"(r[2]), "=r"(r[3]) : "r"(a));
}
__device__ __forceinline__ void ldsm4t(uint32_t a, uint32_t* r) {
    asm volatile("ldmatrix.sync.aligned.m8n8.x4.trans.shared.b16 {%0,%1,%2,%3}, [%4];" : "=r"(r[0]), "=r"(r[1]), "=r"(r[2]), "=r"(r[3]) : "r"(a));
}
__device__ __forceinline__ float rcp(float x) { float r; asm("rcp.approx.ftz.f32 %0, %1;" : "=f"(r) : "f"(x)); return r; }
__device__ __forceinline__ uint2 ld_relaxed2(const void* p) { uint2 v; asm volatile("ld.relaxed.gpu.global.v2.u32 {%0,%1}, [%2];" : "=r"(v.x), "=r"(v.y) : "l"(p) : "memory"); return v; }
__device__ __forceinline__ void st_relaxed2(void* p, uint32_t x, uint32_t y) { asm volatile("st.relaxed.gpu.global.v2.u32 [%0], {%1,%2};" ::"l"(p), "r"(max(x, 1u)), "r"(max(y, 1u)) : "memory"); }
__device__ __forceinline__ constexpr uint64_t dconst(uint32_t lbo, uint32_t sbo, uint32_t swz) {
    return ((uint64_t)(lbo >> 4) << 16) | ((uint64_t)(sbo >> 4) << 32) | ((uint64_t)swz << 62);
}
__device__ __forceinline__ uint64_t mkdesc(uint32_t addr, uint64_t c) { return c | (uint64_t)((addr & 0x3FFFF) >> 4); }
#define WG_FENCE() asm volatile("wgmma.fence.sync.aligned;" ::: "memory")
#define WG_COMMIT() asm volatile("wgmma.commit_group.sync.aligned;" ::: "memory")
#define WG_WAIT(n) asm volatile("wgmma.wait_group.sync.aligned %0;" ::"n"(n) : "memory")
template <int N> __device__ __forceinline__ void reg_fence(float* d) {
#pragma unroll
    for (int i = 0; i < N; i++) asm volatile("" : "+f"(d[i])::"memory");
}
template <int N> __device__ __forceinline__ void reg_def(float* d) {
#pragma unroll
    for (int i = 0; i < N; i++) asm volatile("" : "=f"(d[i]));
}
template <int N> __device__ __forceinline__ void reg_def(uint32_t* d) {
#pragma unroll
    for (int i = 0; i < N; i++) asm volatile("" : "=r"(d[i]));
}
__device__ __forceinline__ bool is_unset(uint4 v) { return min(min(v.x, v.y), min(v.z, v.w)) == 0u; }
__device__ __forceinline__ uint4 nz4(uint32_t a, uint32_t b, uint32_t c, uint32_t d) { return make_uint4(max(a, 1u), max(b, 1u), max(c, 1u), max(d, 1u)); }
__device__ __forceinline__ void wait_flag(const uint32_t* p, uint32_t target) {
    int n = 0;
    while ((int)(ld_relaxed(p) - target) < 0) { if (++n > SPIN_LIMIT) __trap(); }
    asm volatile("fence.acquire.gpu;" ::: "memory");
}
__device__ __forceinline__ float silu_bf(uint32_t cbits) {
    const float c = __uint_as_float(cbits << 16);
    return bf_round(__fdividef(c, 1.f + fminf(ex2(-1.4426950408889634f * c), 1e30f)));
}
__device__ __forceinline__ void gemv_part(uint32_t wmbuf, int npanel, int wp, int lane) {
    const uint32_t wa = wmbuf + wp * 512 + (8 * (lane >> 4) + (lane & 7)) * 32 + ((lane >> 3) & 1) * 16;
    uint2 B[4];
#pragma unroll
    for (int i = 0; i < 4; i++) { const float2 v = lds2f(wmbuf + 28672 + (wp + 8 * i) * 32 + (lane & 3) * 8); B[i] = make_uint2(__float_as_uint(v.x), __float_as_uint(v.y)); }
#pragma unroll 1
    for (int pn = 0; pn < npanel; pn++) {
        float d[4] = {};
        uint32_t A[16];
#pragma unroll
        for (int i = 0; i < 4; i++) ldsm4t(wa + pn * 14336 + (i < 3 || wp < 4 ? i : 0) * 4096, A + 4 * i);
#pragma unroll
        for (int i = 0; i < 4; i++) mma16816(d, A[4 * i], A[4 * i + 1], A[4 * i + 2], A[4 * i + 3], B[i].x, B[i].y);
        if ((lane & 3) == 0) {
            sts1(wmbuf + 29696 + (wp * 32 + pn * 16 + (lane >> 2)) * 4, __float_as_uint(d[0]));
            sts1(wmbuf + 29696 + (wp * 32 + pn * 16 + 8 + (lane >> 2)) * 4, __float_as_uint(d[2]));
        }
    }
}
__device__ __forceinline__ int pass_f(int fs, int ps) { return 224 * fs + ((fs & 1) ? (ps == 0 ? 96 : ps == 1 ? 32 : 0) : (ps == 0 ? 0 : ps == 1 ? 128 : 192)); }
__device__ __forceinline__ constexpr uint32_t slot_off(int l) { return (l < 3 || l > 6 ? l : l == 6 ? 3 : l + 1) * 16384; }
__device__ __forceinline__ void ln_coeffs(float mean, float msq, uint32_t& r2, uint32_t& n2) {
    const float rs = bf_round(rsqrtf(fmaxf(msq - mean * mean, 0.f) + 1e-5f));
    r2 = pack2(rs, rs);
    n2 = pack2(-mean * rs, -mean * rs);
}

template <int sec> __device__ __forceinline__ void ring_loader(const Params& p, uint32_t sb_, int r_, int j_) {
    const uint32_t sb = opaque(sb_);
    const int r = opaque(r_), j = opaque(j_), nq = j >> 1, fs = 4 * (j & 1) + nq;
    const int fa = pass_f(fs, 0), fb = pass_f(fs, 1), fc = pass_f(fs, 2);
#define BAR(i) (sb + M_BAR + 8 * (i))
#define kh (j & 1)
            int sl = 0;
#pragma unroll 1
            for (int s = 0; s < 28; s++) {
                if (s >= 1 && s < 6) mbar_wait(BAR(B_FULL + s - 1), 0);
                const int ps = s < 14 ? 0 : s < 21 ? 1 : 2;
                const uint32_t half = ps < 2 ? 8192 : 4096;
                mbar_wait(BAR(B_EMPTY + sl), (s >= 7 && s < 14) || s >= 21);
                expect_e(BAR(B_FULL + sl), half);
                tma3_e(sb + slot_off(sl) + sec * half, &p.ga + 2 * ps + sec, 0, ps ? 64 * sl : 32 * s, ps == 0 ? fa >> 6 : ps == 1 ? fb >> 6 : fc >> 5, BAR(B_FULL + sl));
                sl = sl == 6 ? 0 : sl + 1;
            }
            if (!sec) PROFH(3);
#pragma unroll 1
            for (int e = 0; e < 4; e++) {
                const uint32_t dst = sb + slot_off(e) + sec * 8192, bar = BAR(B_FULL + e);
                const int f = (e < 2 ? fa + 64 * e : e == 2 ? fb : fc) + 32 * sec;
                mbar_wait(BAR(B_EMPTY + e), 0);
                expect_e(bar, e == 3 && sec ? 0 : 8192);
                if (!(e == 3 && sec)) { tma3_e(dst, &p.dn, 112 * nq + 48, f, 0, bar); tma3_e(dst + 4096, &p.dn, 112 * nq, f, 0, bar); }
            }
            sl = 4;
            int e = 4;
#pragma unroll 1
            for (int grp = 0; grp < 9; grp++) {
                const int ps = grp >= 6 ? 2 : grp >= 3 ? 1 : 0;
                int sidx = grp - 3 * ps;
                if (sec && sidx == 0) { mbar_wait(BAR(B_HRDY + ps), 0); fence_async_global(); }
                sidx += sidx >= nq;
                int f = pass_f(4 * kh + sidx, ps);
#pragma unroll 1
                for (int k = 4 >> ps; k > 0; k--, e++, f += 32) {
                    const uint32_t dst = sb + slot_off(sl), bar = BAR(B_FULL + sl);
                    mbar_wait(BAR(B_EMPTY + sl), e >= 12 && e < 24);
                    if (e < WIN_END) mbar_wait(BAR(B_FULL + (sl >= WIN ? sl - WIN : sl + 12 - WIN)), e - WIN >= 12);
                    expect_e(bar, 8192);
                    if (!sec) { tma3_e(dst, &p.dn, 112 * nq + 48, f, 0, bar); tma3_e(dst + 4096, &p.dn, 112 * nq, f, 0, bar); }
                    else bulk_e(dst + 8192, g_h2 + (size_t)r * (224 * 512) + f * 64, 8192, bar);
                    sl = sl == 11 ? 0 : sl + 1;
                }
            }
            if (!sec) PROFH(4);
}

__global__ void __cluster_dims__(2, 1, 1) __launch_bounds__(384, 1) fused_block_kernel(const __grid_constant__ Params p) {
    extern __shared__ __align__(1024) unsigned char smem[];
    const uint32_t sb = (uint32_t)__cvta_generic_to_shared(smem);
    const int tid = threadIdx.x, lane = tid & 31, warp = __shfl_sync(~0u, tid >> 5, 0);
    const int m = blockIdx.x >> 1;
    int r, nq;
    {
        int g, i;
        if (m < MAP_S) { g = m < 4 ? 15 : 16; i = m & 3; }
        else if (m < MAP_S + 32) { g = (m - MAP_S) & 7; i = (m - MAP_S) >> 3; }
        else if (m < MAP_S + 60) { i = (m - MAP_S - 32) / 7; g = 8 + (m - MAP_S - 32) - 7 * i; }
        else { g = 16; i = m & 3; }
        r = g; nq = i;
    }
    const int j = opaque(2 * nq + (blockIdx.x & 1)), b = 8 * r + j, fs = 4 * kh + nq;
    const uint32_t sc = r == 16;
    if (lane == 0 && warp < 9 && warp != 6 && warp != 7) {
        const int i0 = warp == 8 ? 0 : 8 + 8 * warp, cnt = warp == 0 || warp == 8 ? 1 : warp < 3 ? 2 : 8;
#pragma unroll
        for (int k = 0; k < 8; k++) if (i0 + k != B_WMFULL) mbar_init(BAR(i0 + k), cnt);
        asm volatile("fence.mbarrier_init.release.cluster;" ::: "memory");
        fence_async_smem();
    }

    if (warp < 8) {
        const int w = warp >> 2, wi = warp & 3;
#define COORDS const int t = fresh_tid() & 127, lane = t & 31, q = lane & 3, lr = lane >> 2, ra = 64 * w + 16 * wi + lr; \
        const uint32_t lx = (lane >> 4) ^ (lane & 7), mrow = (64 * w + 16 * wi + ((lane >> 3) & 1) * 8 + (lane & 7)) * 128; \
        (void)q; (void)lr; (void)ra; (void)lx; (void)mrow;
        const int sid = 2 * (j & 3) + w;
#define RUN(k) (!sc || sid == (k))
#define WAIT(i, par) mbar_wait_c(BAR(i), (par) | sc)
        constexpr uint64_t DB128 = dconst(4096, 1024, 1);
        bar_arrive(9, 384);
        bar_sync(0, 384);
        asm volatile("barrier.cluster.arrive.relaxed.aligned;" ::: "memory");
        asm volatile("setmaxnreg.inc.sync.aligned.u32 224;");
        PROFC(0);
        uint32_t xr[16];
        {
            COORDS
            uint32_t h[112];
            if (RUN(0)) {
                float ds[4] = {}, da[2][4] = {}, db[2][4] = {};
                const uint32_t ONE2 = 0x3F803F80u;
                if (kh == 0) { WAIT(B_WMFULL, 0); gemv_part(sb + OFF_Y + HALF, 1, warp, lane); warp_arrive(BAR(B_GEMV)); }
#pragma unroll
                for (int kb = 0; kb < 7; kb++) {
                    WAIT(B_XFULL + kb, 0);
#pragma unroll
                    for (int k4 = 0; k4 < 4; k4++) ldsm4(sb + OFF_X + mrow + kb * 16384 + (((2 * k4) ^ lx) << 4), h + 16 * kb + 4 * k4);
#pragma unroll
                    for (int k4 = 0; k4 < 4; k4++) {
                        const uint32_t* f = h + 16 * kb + 4 * k4;
                        mma16816(ds, f[0], f[1], f[2], f[3], ONE2, ONE2);
                        mma1688(da[0], f[0], f[1], f[0]); mma1688(db[0], f[0], f[1], f[1]);
                        mma1688(da[1], f[2], f[3], f[2]); mma1688(db[1], f[2], f[3], f[3]);
                    }
                }
#pragma unroll
                for (int i = 0; i < 4; i++) {
                    const int ch = 7 * j + 2 * i + (lane >> 4);
                    ldsm4(sb + OFF_X + mrow + (ch >> 3) * 16384 + (((ch ^ lane) & 7) << 4), xr + 4 * i);
                }
                warp_arrive(BAR(B_XFREE));
                float qa = (lr & 1) ? da[0][1] + da[1][1] : da[0][0] + da[1][0];
                float qb = (lr & 1) ? db[0][3] + db[1][3] : db[0][2] + db[1][2];
                const int src = (lane & ~3) | (lr >> 1);
                qa = __shfl_sync(~0u, qa, src);
                qb = __shfl_sync(~0u, qb, src);
                uint32_t ra2, na2, rb2, nb2;
                ln_coeffs(ds[0] * (1.f / DM), qa * (1.f / DM), ra2, na2);
                ln_coeffs(ds[2] * (1.f / DM), qb * (1.f / DM), rb2, nb2);
#pragma unroll
                for (int i = 0; i < 112; i += 2) { h[i] = hfma2(h[i], ra2, na2); h[i + 1] = hfma2(h[i + 1], rb2, nb2); }
                if (kh == 1) { WAIT(B_WMFULL, 0); gemv_part(sb + OFF_Y + HALF, 2, warp, lane); warp_arrive(BAR(B_GEMV)); }
            } else { reg_def<112>(h); reg_def<16>(xr); }
            PROFC(1);
            if (RUN(1)) {
                float ak[28], av[28], aq[28];
                uint32_t kp[14], vp[14];
                const uint64_t bk0 = mkdesc(sb + OFF_Y, DB128) + kh, bv0 = mkdesc(sb + OFF_Y + HALF, DB128) + kh, bq0 = mkdesc(sb + OFF_X, DB128) + kh;
                uint32_t* kvg = g_kv + (size_t)(b * 2) * 3584 + (8 * w + 2 * wi) * 224 + lane;
                WAIT(B_FULLK, 0);
                WAIT(B_MOD1, 0);
                PROFC(2);
                reg_def<28>(ak);
#pragma unroll
                for (int g4 = 0; g4 < 4; g4++) {
#pragma unroll
                    for (int ks = 7 * g4; ks < 7 * g4 + 7; ks++) {
                        const uint4 st = *(const uint4*)(smem + M_ST + ks * 64 + q * 16);
                        h[4 * ks] = hfma2(h[4 * ks], st.x, st.y); h[4 * ks + 1] = hfma2(h[4 * ks + 1], st.x, st.y);
                        h[4 * ks + 2] = hfma2(h[4 * ks + 2], st.z, st.w); h[4 * ks + 3] = hfma2(h[4 * ks + 3], st.z, st.w);
                    }
                    WG_FENCE();
#pragma unroll
                    for (int ks = 7 * g4; ks < 7 * g4 + 7; ks++) wgmma_rs_56<1>(ak, h[4 * ks], h[4 * ks + 1], h[4 * ks + 2], h[4 * ks + 3], bk0 + ks * 128, ks != 0);
                }
                WG_COMMIT();
                PROFC(3);
                WAIT(B_FULLV, 0);
                reg_def<28>(av);
                WG_FENCE();
#pragma unroll
                for (int ks = 0; ks < 8; ks++) wgmma_rs_56<1>(av, h[4 * ks], h[4 * ks + 1], h[4 * ks + 2], h[4 * ks + 3], bv0 + ks * 128, ks != 0);
                WG_COMMIT();
                WG_WAIT(1);
                reg_fence<28>(ak);
#pragma unroll
                for (int g = 0; g < 7; g++) {
                    kp[2 * g] = pack2(ak[4 * g], ak[4 * g + 1]); kp[2 * g + 1] = pack2(ak[4 * g + 2], ak[4 * g + 3]);
                    kvg[g * 32] = kp[2 * g]; kvg[224 + g * 32] = kp[2 * g + 1];
                }
                warp_arrive(BAR(B_PUB));
                PROFC(4);
                WG_FENCE();
#pragma unroll
                for (int ks = 8; ks < 28; ks++) wgmma_rs_56<1>(av, h[4 * ks], h[4 * ks + 1], h[4 * ks + 2], h[4 * ks + 3], bv0 + ks * 128, 1);
                WG_COMMIT();
                WAIT(B_FULLQ, 0);
                reg_def<28>(aq);
                WG_FENCE();
#pragma unroll
                for (int ks = 0; ks < 8; ks++) wgmma_rs_56<1>(aq, h[4 * ks], h[4 * ks + 1], h[4 * ks + 2], h[4 * ks + 3], bq0 + ks * 128, ks != 0);
                WG_COMMIT();
                WG_WAIT(1);
                reg_fence<28>(av);
#pragma unroll
                for (int g = 0; g < 7; g++) {
                    vp[2 * g] = pack2(av[4 * g], av[4 * g + 1]); vp[2 * g + 1] = pack2(av[4 * g + 2], av[4 * g + 3]);
                    kvg[3584 + g * 32] = vp[2 * g]; kvg[3584 + 224 + g * 32] = vp[2 * g + 1];
                }
                warp_arrive(BAR(B_PUB + 1));
                PROFC(5);
                WG_FENCE();
#pragma unroll
                for (int ks = 8; ks < 28; ks++) wgmma_rs_56<1>(aq, h[4 * ks], h[4 * ks + 1], h[4 * ks + 2], h[4 * ks + 3], bq0 + ks * 128, 1);
                WG_COMMIT();
                WAIT(B_PUB + 1, 0);
                const uint32_t ko = sb + OFF_Y + Y_KOWN + (8 * w + 2 * wi) * 896 + lane * 4;
                const uint32_t qo = sb + OFF_Y + Y_Q + (8 * w + 2 * wi) * 1024 + lane * 4;
#pragma unroll
                for (int g = 0; g < 7; g++) {
                    sts1(ko + g * 128, kp[2 * g]); sts1(ko + 896 + g * 128, kp[2 * g + 1]);
                    sts1(ko + (Y_VOWN - Y_KOWN) + g * 128, vp[2 * g]); sts1(ko + (Y_VOWN - Y_KOWN) + 896 + g * 128, vp[2 * g + 1]);
                }
                WG_WAIT(0);
                reg_fence<28>(aq);
                __syncwarp();
                if (lane < 3 && w == 1) mbar_arrive(BAR(B_EMPTY + lane));
#pragma unroll
                for (int g = 0; g < 7; g++) {
                    const uint32_t q0 = pack2(aq[4 * g], aq[4 * g + 1]), q1 = pack2(aq[4 * g + 2], aq[4 * g + 3]);
                    if (g == 3) {
                        sts1(qo + 3 * 128, q < 2 ? q0 : 0u); sts1(qo + 1024 + 3 * 128, q < 2 ? q1 : 0u);
                        sts1(qo + 4 * 128, q < 2 ? 0u : q0); sts1(qo + 1024 + 4 * 128, q < 2 ? 0u : q1);
                    } else {
                        const int ch = g < 3 ? g : g + 1;
                        sts1(qo + ch * 128, q0); sts1(qo + 1024 + ch * 128, q1);
                    }
                }
                if (!sc) bar_sync(3, 256);
            }
        }
        PROFC(6);
        WAIT(B_KRFULL, 0);
        PROFC(7);
        if (RUN(2)) {
#pragma unroll 1
            for (int hf = sc; hf < 2; hf++) {
                COORDS
                float s[136];
                float na = 0.f, nb = 0.f;
                const float CS = 0.18898223650461361f * 1.4426950408889634f;
                const int kg0 = 8 * hf + 2 * wi;
                const int pmin = 16 - 8 * r - 4 * hf - wi;
                const float NEG = __int_as_float(0xFF800000);
                {
                    uint32_t F[8];
                    const uint32_t qa = sb + OFF_Y + Y_Q + (kg0 + ((lane >> 3) & 1)) * 1024 + (4 * w + (lane >> 4)) * 128 + (lane & 7) * 16;
                    ldsm4(qa, F); ldsm4(qa + 256, F + 4);
                    uint32_t ka = sb + OFF_Y + Y_K + kg0 * 896 + (3 * w + (lane >> 3)) * 128 + (lane & 7) * 16;
#pragma unroll
                    for (int g = 0; g < 34; g++) {
                        uint32_t B[4];
                        if (g >= 12 && g % 4 == 0) ka += __float_as_uint(s[4 * (g - 12)]) & p.zero;
                        ldsm4(ka + g * 896, B);
                        mma16816_first(s + 4 * g, F[0], F[1], F[2], F[3], B[0], B[1]);
                        mma16816_v(s + 4 * g, F[4], F[5], F[6], F[7], B[2], B[3]);
                    }
                    const bool c0 = 2 * q > lr, c1 = 2 * q + 1 > lr;
                    if (!c0) { s[0] = NEG; s[6] = NEG; }
                    if (!c1) { s[1] = NEG; s[7] = NEG; }
                    s[2] = NEG; s[3] = NEG;
                    if (c0) { s[128] = NEG; s[134] = NEG; }
                    if (c1) { s[129] = NEG; s[135] = NEG; }
                    s[132] = NEG; s[133] = NEG;
                    float ma = NEG, mb = NEG;
#pragma unroll
                    for (int pp = 0; pp < 17; pp++) {
                        const float* e = s + 8 * pp;
                        const float bias = pp < pmin ? NEG : 0.f;
                        ma = fmaxf(ma, fmaxf(fmaxf(e[0], e[1]), fmaxf(e[4], e[5])) + bias);
                        mb = fmaxf(mb, fmaxf(fmaxf(e[2], e[3]), fmaxf(e[6], e[7])) + bias);
                    }
                    ma = fmaxf(ma, __shfl_xor_sync(~0u, ma, 1)); mb = fmaxf(mb, __shfl_xor_sync(~0u, mb, 1));
                    ma = fmaxf(ma, __shfl_xor_sync(~0u, ma, 2)); mb = fmaxf(mb, __shfl_xor_sync(~0u, mb, 2));
                    na = -ma * CS; nb = -mb * CS;
                }
                PROFC(8 + 3 * hf);
                {
                    WAIT(B_VRFULL, 0);
                    float o[16] = {}, rs[4] = {};
                    const uint32_t va = sb + OFF_Y + Y_VR + (kg0 + ((lane >> 3) & 1)) * 896 + (3 * w + (lane >> 4)) * 128 + (lane & 7) * 16;
#pragma unroll
                    for (int pp = 0; pp < 17; pp++) {
                        uint32_t B[8];
                        const uint32_t v = va + pp * 1792 + (pp == 16 || (pp >= 9 && kg0 + 2 * pp >= 32) ? Y_VOWN - 32 * 896 : 0);
                        ldsm4t(v, B); ldsm4t(v + 256, B + 4);
                        float e[8];
#pragma unroll
                        for (int i = 0; i < 8; i++) e[i] = ex2(fmaf(s[8 * pp + i], CS, ((i & 2) ? nb : na) + (pp < pmin ? NEG : 0.f)));
                        const uint32_t p0 = pack2(e[0], e[1]), p1 = pack2(e[2], e[3]), p2 = pack2(e[4], e[5]), p3 = pack2(e[6], e[7]);
                        mma16816(rs, p0, p1, p2, p3, 0x3F803F80u, 0x3F803F80u);
#pragma unroll
                        for (int g = 0; g < 4; g++) mma16816(o + 4 * g, p0, p1, p2, p3, B[2 * g], B[2 * g + 1]);
                    }
                    PROFC(9 + 3 * hf);
                    const float ia = rcp(rs[0]), ib = rcp(rs[2]);
                    uint32_t* og = g_o + (size_t)(2 * r + hf) * 14336 + (7 * j + 3 * w) * 256 + wi * 64 + lane;
#pragma unroll
                    for (int g = 0; g < 4; g++) {
                        if ((g == 3 - 3 * w) ? ((q >> 1) == w) : true) {
                            og[g * 256] = pack2(o[4 * g] * ia, o[4 * g + 1] * ia);
                            og[g * 256 + 32] = pack2(o[4 * g + 2] * ib, o[4 * g + 3] * ib);
                        }
                    }
                    warp_arrive(BAR(B_PUB + 2 + hf));
                    PROFC(10 + 3 * hf);
                }
            }
        }
        uint32_t x1p[14];
        COORDS
        constexpr uint64_t DT = dconst(1024, 128, 0);
        if (RUN(4)) {
            float ac[28];
            const uint64_t ad = mkdesc(sb + (w ? OFF_Y + HALF : OFF_X), DT), bd = mkdesc(sb + OFF_X + HALF, DB128) + kh;
            WAIT(B_WOFULL, 0);
            WAIT(B_MOD2, 0);
            WAIT(B_GFULL + w, 0);
            PROFC(28);
            reg_def<28>(ac);
#pragma unroll 1
            for (int u = 0; u < 4; u++) {
                WG_FENCE();
#pragma unroll
                for (int i = 0; i < 7; i++) wgmma_ss_56<1>(ac, ad + (7 * u + i) * 128, bd + (7 * u + i) * 128, (u | i) != 0);
            }
            WG_COMMIT();
            WG_WAIT(0);
            reg_fence<28>(ac);
            PROFC(14);
            __syncwarp();
            if (lane < 3) mbar_arrive(BAR(B_EMPTY + 3 + lane));
            if (lane < 3 && w == 0) mbar_arrive(BAR(B_EMPTY + lane));
            float s1a = 0.f, s2a = 0.f, s1b = 0.f, s2b = 0.f;
            uint32_t* xo = g_x1 + (size_t)(2 * r + w) * 14336 + 7 * j * 256 + wi * 64 + lane;
#pragma unroll
            for (int g = 0; g < 7; g++) {
                const float2 ga = *(const float2*)(smem + M_G + (8 * g + 2 * q) * 4);
                x1p[2 * g] = pack2(fmaf(ga.x, ac[4 * g], bf_lo(xr[2 * g])), fmaf(ga.y, ac[4 * g + 1], bf_hi(xr[2 * g])));
                x1p[2 * g + 1] = pack2(fmaf(ga.x, ac[4 * g + 2], bf_lo(xr[2 * g + 1])), fmaf(ga.y, ac[4 * g + 3], bf_hi(xr[2 * g + 1])));
                xo[g * 256] = x1p[2 * g]; xo[g * 256 + 32] = x1p[2 * g + 1];
                const float u0 = bf_lo(x1p[2 * g]), u1 = bf_hi(x1p[2 * g]), u2 = bf_lo(x1p[2 * g + 1]), u3 = bf_hi(x1p[2 * g + 1]);
                s1a += u0 + u1; s2a += u0 * u0 + u1 * u1; s1b += u2 + u3; s2b += u2 * u2 + u3 * u3;
            }
            float ka = (q & 1) ? s2a : s1a, kb2 = (q & 1) ? s2b : s1b;
            ka += __shfl_xor_sync(~0u, (q & 1) ? s1a : s2a, 1); kb2 += __shfl_xor_sync(~0u, (q & 1) ? s1b : s2b, 1);
            const float kk = ((q & 2) ? kb2 : ka) + __shfl_xor_sync(~0u, (q & 2) ? ka : kb2, 2);
            ((float*)g_st)[(((2 * r + w) * 8 + j) * 64 + 16 * wi + lr + 4 * (q & 2)) * 2 + (q & 1)] = kk;
            __syncwarp();
            if (lane < 2) mbar_arrive(BAR(B_PUB + 4 + w));
        } else reg_def<14>(x1p);
        PROFC(15);
        uint32_t h2a[32], h2b[24];
        if (RUN(6)) {
            const int fa = pass_f(fs, 0), fb = pass_f(fs, 1), fc = pass_f(fs, 2);
            uint32_t* h2g = g_h2 + (size_t)r * (224 * 512) + (8 * w + 2 * wi) * 32 + lane;
            const uint64_t a0 = mkdesc(sb + OFF_Y + w * HALF, DT);
            {
                WAIT(B_GFULL + 2 + w, 0);
                PROFC(16);
                float2 sa = make_float2(0.f, 0.f), sbb = sa;
#pragma unroll
                for (int jj = 0; jj < 8; jj++) {
                    const float2 u = lds2f(sb + OFF_X + X_STAT + w * 4096 + (jj * 64 + 16 * wi + lr) * 8), v = lds2f(sb + OFF_X + X_STAT + w * 4096 + (jj * 64 + 16 * wi + lr + 8) * 8);
                    sa.x += u.x; sa.y += u.y; sbb.x += v.x; sbb.y += v.y;
                }
                warp_arrive(BAR(B_EMPTY + 6));
                uint32_t ra2, na2, rb2, nb2;
                ln_coeffs(sa.x * (1.f / DM), sa.y * (1.f / DM), ra2, na2);
                ln_coeffs(sbb.x * (1.f / DM), sbb.y * (1.f / DM), rb2, nb2);
                const uint32_t ha = sb + OFF_Y + w * HALF + (lane >> 4) * 1024 + (2 * wi + ((lane >> 3) & 1)) * 128 + (lane & 7) * 16;
                const uint32_t sta = sb + M_ST + q * 16;
                auto prep = [&](int s, uint32_t* f) {
                    uint32_t x[8];
                    ldsm4(ha + s * 4096, x); ldsm4(ha + s * 4096 + 2048, x + 4);
                    const uint4 st[2] = {lds4(sta + s * 128), lds4(sta + s * 128 + 64)};
#pragma unroll
                    for (int i = 0; i < 2; i++) {
                        f[4 * i] = hfma2(hfma2(x[4 * i], ra2, na2), st[i].x, st[i].y); f[4 * i + 1] = hfma2(hfma2(x[4 * i + 1], rb2, nb2), st[i].x, st[i].y);
                        f[4 * i + 2] = hfma2(hfma2(x[4 * i + 2], ra2, na2), st[i].z, st[i].w); f[4 * i + 3] = hfma2(hfma2(x[4 * i + 3], rb2, nb2), st[i].z, st[i].w);
                    }
                    stsm4(ha + s * 4096, f[0], f[1], f[2], f[3]); stsm4(ha + s * 4096 + 2048, f[4], f[5], f[6], f[7]);
                };
                float ac[128];
                uint32_t fr[3][8];
                const uint64_t bx = mkdesc(sb, DB128);
                reg_def<128>(ac);
                prep(0, fr[0]);
                PROFC(17);
#pragma unroll
                for (int s = 0; s < 14; s++) {
                    const uint32_t* f = fr[s % 3];
                    const uint64_t bd = bx + (slot_off(s % 7) >> 4);
                    WAIT(B_FULL + s % 7, s >= 7);
                    WG_FENCE();
                    wgmma_rs_256<1>(ac, f[0], f[1], f[2], f[3], bd, s != 0);
                    wgmma_rs_256<1>(ac, f[4], f[5], f[6], f[7], bd + 128, 1);
                    WG_COMMIT();
                    if (s < 13) prep(s + 1, fr[(s + 1) % 3]);
                    if (s > 0) { WG_WAIT(1); warp_arrive(BAR(B_EMPTY + (s - 1) % 7)); }
                }
                PROFC(18);
                fence_async_smem();
                WG_WAIT(0);
                reg_fence<128>(ac);
                warp_arrive(BAR(B_EMPTY + 6));
#pragma unroll
                for (int g = 0; g < 16; g++) {
                    h2a[2 * g] = hmul2(pack2_relu(ac[4 * g], ac[4 * g + 1]), pack2(ac[64 + 4 * g], ac[64 + 4 * g + 1]));
                    h2a[2 * g + 1] = hmul2(pack2_relu(ac[4 * g + 2], ac[4 * g + 3]), pack2(ac[64 + 4 * g + 2], ac[64 + 4 * g + 3]));
                    h2g[(fa / 8 + g) * 512] = h2a[2 * g]; h2g[(fa / 8 + g) * 512 + 32] = h2a[2 * g + 1];
                }
                warp_arrive(BAR(B_PUB + 6));
                bar_sync(1 + w, 128);
            }
            PROFC(19);
            {
                float ac[64];
                reg_def<64>(ac);
                const uint64_t bx = mkdesc(sb, dconst(8192, 1024, 1));
#pragma unroll kB
                for (int s = 0; s < 7; s++) {
                    WAIT(B_FULL + s, 0);
                    const uint64_t ad = a0 + s * 512, bd = bx + (slot_off(s) >> 4);
                    WG_FENCE();
#pragma unroll
                    for (int k = 0; k < 4; k++) wgmma_ss_128<1>(ac, ad + k * 128, bd + k * 128, (s | k) != 0);
                    WG_COMMIT();
                    if (s > 0) { WG_WAIT(1); warp_arrive(BAR(B_EMPTY + s - 1)); }
                }
                WG_WAIT(0);
                reg_fence<64>(ac);
                warp_arrive(BAR(B_EMPTY + 6));
#pragma unroll
                for (int g = 0; g < 8; g++) {
                    h2b[2 * g] = hmul2(pack2_relu(ac[4 * g], ac[4 * g + 1]), pack2(ac[32 + 4 * g], ac[32 + 4 * g + 1]));
                    h2b[2 * g + 1] = hmul2(pack2_relu(ac[4 * g + 2], ac[4 * g + 3]), pack2(ac[32 + 4 * g + 2], ac[32 + 4 * g + 3]));
                    h2g[(fb / 8 + g) * 512] = h2b[2 * g]; h2g[(fb / 8 + g) * 512 + 32] = h2b[2 * g + 1];
                }
                warp_arrive(BAR(B_PUB + 7));
            }
            PROFC(27);
            {
                float ac[32];
                reg_def<32>(ac);
                const uint64_t bx = mkdesc(sb, dconst(4096, 512, 2));
#pragma unroll kC
                for (int s = 0; s < 7; s++) {
                    WAIT(B_FULL + s, 1);
                    const uint64_t ad = a0 + p.zero + s * 512, bd = bx + (slot_off(s) >> 4);
                    WG_FENCE();
#pragma unroll
                    for (int k = 0; k < 4; k++) wgmma_ss_64<1>(ac, ad + k * 128, bd + k * 64, (s | k) != 0);
                    WG_COMMIT();
                    if (s > 0) { WG_WAIT(1); warp_arrive(BAR(B_EMPTY + s - 1)); }
                }
                WG_WAIT(0);
                reg_fence<32>(ac);
                __syncwarp();
                if (lane < 6) mbar_arrive(BAR(B_EMPTY + 6 + lane));
                PROFC(20);
#pragma unroll
                for (int g = 0; g < 4; g++) {
                    h2b[16 + 2 * g] = hmul2(pack2_relu(ac[4 * g], ac[4 * g + 1]), pack2(ac[16 + 4 * g], ac[16 + 4 * g + 1]));
                    h2b[16 + 2 * g + 1] = hmul2(pack2_relu(ac[4 * g + 2], ac[4 * g + 3]), pack2(ac[16 + 4 * g + 2], ac[16 + 4 * g + 3]));
                    h2g[(fc / 8 + g) * 512] = h2b[16 + 2 * g]; h2g[(fc / 8 + g) * 512 + 32] = h2b[16 + 2 * g + 1];
                }
                warp_arrive(BAR(B_PUB + 8));
                asm volatile("barrier.cluster.wait.aligned;" ::: "memory");
                if (lane == 0 && !sc) {
                    uint32_t rb;
                    asm volatile("mapa.shared::cluster.u32 %0, %1, %2;" : "=r"(rb) : "r"(BAR(B_PEER)), "r"(kh ^ 1));
                    asm volatile("mbarrier.arrive.relaxed.cluster.shared::cluster.b64 _, [%0];" ::"r"(rb) : "memory");
                }
            }
        } else { reg_def<32>(h2a); reg_def<24>(h2b); }
        PROFC(21);
        if (RUN(7)) {
            float ac[56];
            reg_def<56>(ac);
            constexpr uint64_t DAN = dconst(2048, 128, 0);
            const uint64_t bx = mkdesc(sb, DB128);
#pragma unroll
            for (int e = 0; e < 4; e++) {
                WAIT(B_FULL + e, 0);
                const uint64_t bd = bx + (slot_off(e) >> 4);
                const uint32_t* hh = e < 2 ? h2a + 16 * e : h2b + 16 * (e - 2);
                WG_FENCE();
#pragma unroll
                for (int k = 0; k < (e < 3 ? 4 : 2); k++) wgmma_rs_112<1>(ac, hh[4 * k], hh[4 * k + 1], hh[4 * k + 2], hh[4 * k + 3], bd + (k >> 1) * 512 + (k & 1) * 128, (e | k) != 0);
                WG_COMMIT();
                if (e > 0) { WG_WAIT(1); warp_arrive(BAR(B_EMPTY + e - 1)); }
            }
            PROFC(22);
            const uint64_t ax = mkdesc(sb + 8192 + w * 1024, DAN);
#pragma unroll kG2
            for (int e = 4; e < 25; e++) {
                WAIT(B_FULL + e % 12, e >= 12 && e < 24);
                if (e == 16) PROFC(23);
                const uint64_t z = (e / 12) * p.zero;
                const uint64_t ad = ax + z + (slot_off(e % 12) >> 4), bd = bx + z + (slot_off(e % 12) >> 4);
                WG_FENCE();
                wgmma_ss_112<1>(ac, ad, bd, 1);
                wgmma_ss_112<1>(ac, ad + 256, bd + 128, 1);
                WG_COMMIT();
                if (e < 14) { WG_WAIT(1); warp_arrive(BAR(B_EMPTY + (e - 1) % 12)); }
            }
            mbar_wait_cluster(BAR(B_PEER), sc);
            WG_WAIT(0);
            reg_fence<56>(ac);
            PROFC(24);
            uint32_t rdst, rbar;
            asm volatile("mapa.shared::cluster.u32 %0, %1, %2;" : "=r"(rdst) : "r"(sb + OFF_Y + (5 + w) * 16384 + t * 16), "r"(kh ^ 1 ^ sc));
            asm volatile("mapa.shared::cluster.u32 %0, %1, %2;" : "=r"(rbar) : "r"(BAR(B_XCH + w)), "r"(kh ^ 1 ^ sc));
#define ACG(g, i) ac[4 * (((g) + 8) % 14) + (i)]
#pragma unroll
            for (int g = 0; g < 7; g++) {
                const float v0 = kh ? ACG(g, 0) : ACG(g + 7, 0), v1 = kh ? ACG(g, 1) : ACG(g + 7, 1);
                const float v2 = kh ? ACG(g, 2) : ACG(g + 7, 2), v3 = kh ? ACG(g, 3) : ACG(g + 7, 3);
                if (!sc) asm volatile("st.async.shared::cluster.mbarrier::complete_tx::bytes.v4.f32 [%0], {%1,%2,%3,%4}, [%5];"
                             ::"r"(rdst + g * 2048), "f"(v0), "f"(v1), "f"(v2), "f"(v3), "r"(rbar) : "memory");
            }
            mbar_wait_cluster(BAR(B_XCH + w), sc);
            PROFC(25);
            bf16* og = (sc ? (bf16*)(g_h2 + 16 * 224 * 512) : p.out + (size_t)128 * r * DM) + (size_t)ra * DM + 56 * j + 2 * q;
#pragma unroll
            for (int g = 0; g < 7; g++) {
                const uint4 rv = *(const uint4*)(smem + OFF_Y + (5 + w) * 16384 + t * 16 + g * 2048);
                const float2 gb = *(const float2*)(smem + M_G + 224 + (8 * g + 2 * q) * 4);
                const float v0 = (kh ? ACG(g + 7, 0) : ACG(g, 0)) + __uint_as_float(rv.x), v1 = (kh ? ACG(g + 7, 1) : ACG(g, 1)) + __uint_as_float(rv.y);
                const float v2 = (kh ? ACG(g + 7, 2) : ACG(g, 2)) + __uint_as_float(rv.z), v3 = (kh ? ACG(g + 7, 3) : ACG(g, 3)) + __uint_as_float(rv.w);
                *(uint32_t*)(og + 8 * g) = pack2(fmaf(gb.x, v0, bf_lo(x1p[2 * g])), fmaf(gb.y, v1, bf_hi(x1p[2 * g])));
                *(uint32_t*)(og + 8 * DM + 8 * g) = pack2(fmaf(gb.x, v2, bf_lo(x1p[2 * g + 1])), fmaf(gb.y, v3, bf_hi(x1p[2 * g + 1])));
            }
        }
        PROFC(26);
        bar_sync(1 + w, 128);
        if (wi == 0) warp_arrive(BAR(B_DONE));
    } else {
        const int lane = fresh_tid() & 31;
        const bool early = kh == 0, gemv = r < 14;
        const int mcol = early ? 16 * (4 * r + nq) : 2 * DM + 32 * (4 * r + nq);
        const uint32_t wmbuf = sb + OFF_Y + HALF;
        asm volatile("setmaxnreg.dec.sync.aligned.u32 56;");
        if (warp == 9) {
#pragma unroll
            for (int i = 56; i < 64; i++) init_e(BAR(i), 1);
            fence_async_smem();
        }
        if (warp == 8) { init_e(BAR(B_WMFULL), 2); fence_async_smem(); }
        bar_arrive(0, 384);
        asm volatile("barrier.cluster.arrive.relaxed.aligned;" ::: "memory");
        uint32_t target = 0;
        if (warp == 8) {
            if (!sc) {
                expect_e(BAR(B_WMFULL), gemv ? 28672 >> early : 0);
                if (early && gemv) { tma3_e(wmbuf, &p.wm, mcol, 0, 0, BAR(B_WMFULL)); tma3_e(wmbuf + 7168, &p.wm, mcol, 224, 0, BAR(B_WMFULL)); }
#pragma unroll 1
                for (int kb = 0; kb < 7; kb++) {
                    expect_e(BAR(B_XFULL + kb), 16384);
                    tma3_e(sb + OFF_X + kb * 16384, &p.xm, 64 * kb, 128 * r, 0, BAR(B_XFULL + kb));
                }
            }
#pragma unroll 1
            for (int mt = 0; mt < 4; mt++) {
                if (mt == 1) {
                    if (!early && gemv) {
#pragma unroll 1
                        for (int k = 0; k < 4; k++) tma3_e(wmbuf + k * 7168, &p.wm, mcol + (k >> 1) * 16, (k & 1) * 224, 0, BAR(B_WMFULL));
                    }
                    bar_sync(9, 384);
                    if (sc) return;
                    mbar_wait(BAR(B_MOD1), 0);
                    mbar_wait(BAR(B_WMFREE), 0);
                }
                if (mt == 2) mbar_wait(BAR(B_XFREE), 0);
                if (mt == 3) mbar_wait(BAR(B_VRFULL), 0);
                const uint32_t bar = BAR(mt == 3 ? B_WOFULL : B_FULLK + mt), dst = sb + (mt < 2 ? OFF_Y : OFF_X) + (mt & 1) * HALF;
                const int c0 = (mt < 2 ? DM + DM * mt : 0) + 56 * j - 8 * kh;
                if (!sc) {
                    expect_e(bar, HALF);
                    tma3_e(dst, mt == 3 ? &p.wo : &p.qkv, c0, 0, 0, bar);
                    tma3_e(dst + HALF / 2, mt == 3 ? &p.wo : &p.qkv, c0, 224, 0, bar);
                }
            }
            expect_e(BAR(B_XCH), 14336);
            expect_e(BAR(B_XCH + 1), 14336);
        } else {
            if (warp == 10 && !sc) {
                l2_prefetch_e((const char*)p.wqkv + (size_t)b * 9408, 9408);
                if (lane == 0) sts1(sb + M_EPOCH, atomicAdd(&g_ticket, 1u) / NCTA);
            }
            if (warp == 11) {
#pragma unroll
                for (int i = 0; i < 8; i++) {
                    const int wd = lane + 32 * i;
                    const uint32_t cb = i < 7 ? __ldg((const uint32_t*)p.c + wd) : 0u;
                    sts1(wmbuf + 28672 + (wd >> 3) * 32 + (wd & 3) * 8 + (wd & 4), pack2(silu_bf(cb & 0xFFFFu), silu_bf(cb >> 16)));
                }
            }
            bar_sync(9, 384);
            if (sc) return;
            target = lds1(sb + M_EPOCH) + 1;
            const uint32_t tag = target & 0xFFFFu;
            if (warp == 11) {
                warp_arrive(BAR(B_WMFULL));
                mbar_wait(BAR(B_GEMV), 0);
                float sum = 0.f;
#pragma unroll
                for (int i = 0; i < 8; i++) sum += *(const float*)(smem + OFF_Y + HALF + 29696 + (i * 32 + (early ? lane & 15 : lane)) * 4);
                const uint32_t word = (pack2(sum, 0.f) << 16) | tag;
                if (gemv) {
                    uint32_t* mg = g_mod + mcol + (early ? (lane & 15) + (lane >> 4) * 4 * 6 * DM : lane);
#pragma unroll
                    for (int i = 0; i < 8; i++) if (i < 4 || !early) st_relaxed(mg + i * 6 * DM, word);
                }
                warp_arrive(BAR(B_WMFREE));
            }
            const uint4* modp = (const uint4*)g_mod + (r & 7) * (6 * DM / 4);
            const bool p2 = warp == 11;
            mbar_wait(BAR(p2 ? B_PUB : B_XFULL + 4), 0);
#pragma unroll 1
            for (int it = p2 ? 0 : warp - 9; it < (p2 ? 2 : warp - 8); it++) {
                const int i0 = lane + 32 * it, imax = p2 ? 251 : 223;
                uint4 v[4];
#pragma unroll 1
                for (int n = 0;; n++) {
                    uint32_t bad = 0;
#pragma unroll
                    for (int k = 0; k < 4; k++) {
                        const int i = min(i0 + 64 * k, imax);
                        v[k] = ld_relaxed4(modp + (i < 224 ? (p2 ? 336 : 0) + i : (i < 238 ? 14 * j + i : 14 * j + i + 322)));
                        bad |= (v[k].x ^ tag) | (v[k].y ^ tag) | (v[k].z ^ tag) | (v[k].w ^ tag);
                    }
                    if (!__any_sync(~0u, bad & 0xFFFFu)) break;
                    if (n > SPIN_LIMIT) __trap();
                }
#pragma unroll
                for (int k = 0; k < 4; k++) {
                    const int i = min(i0 + 64 * k, imax);
                    if (i < 224) {
                        const int isc = i >= 112, c4 = i - 112 * isc;
                        const float one = isc ? 1.f : 0.f;
                        const uint32_t a = sb + M_ST + (c4 >> 2) * 64 + (c4 & 1) * 32 + (c4 & 2) * 4 + (isc ? 0 : 4);
                        sts1(a, pack2(bf_hi(v[k].x) + one, bf_hi(v[k].y) + one));
                        sts1(a + 16, pack2(bf_hi(v[k].z) + one, bf_hi(v[k].w) + one));
                    } else {
                        sts4(sb + M_G + (i - 224) * 16, make_uint4(v[k].x & 0xFFFF0000u, v[k].y & 0xFFFF0000u, v[k].z & 0xFFFF0000u, v[k].w & 0xFFFF0000u));
                    }
                }
                warp_arrive(BAR(p2 ? B_MOD2 : B_MOD1));
            }
            if (warp == 9) {
#pragma unroll 1
                for (int kv = 0; kv < 2; kv++) {
                    mbar_wait(BAR(B_PUB + kv), 0);
                    if (lane >= 1 && lane <= 2 && r >= lane) wait_flag(g_flag + kv * 128 + b - 8 * lane, target);
                    __syncwarp();
                    fence_async_global();
                    const uint32_t dst = sb + OFF_Y + (kv ? Y_VR : Y_K);
                    expect_e(BAR(B_KRFULL + kv), r >= 2 ? 28672 : r == 1 ? 14336 : 0);
                    if (r >= 2) bulk_e(dst, g_kv + (size_t)((b - 16) * 2 + kv) * 3584, 14336, BAR(B_KRFULL + kv));
                    if (r >= 1) bulk_e(dst + 14336, g_kv + (size_t)((b - 8) * 2 + kv) * 3584, 14336, BAR(B_KRFULL + kv));
                }
            } else if (warp == 11) {
                mbar_wait(BAR(B_VRFULL), 0);
                l2_prefetch_e((const char*)p.wg + (size_t)b * 12544, 12544);
                l2_prefetch_e((const char*)p.wu + (size_t)b * 12544, 12544);
                l2_prefetch_e((const char*)p.wd + (size_t)b * 12544, 12544);
            }
        }
        if (warp == 8 || warp == 11) {
            const int sec = warp == 11;
            if (sec) ring_loader<1>(p, sb, r, j); else ring_loader<0>(p, sb, r, j);
            mbar_wait(BAR(B_DONE), 0);
        } else if (warp == 9) {
#pragma unroll
            for (int ev = 0; ev < 4; ev++) expect_e(BAR(B_GFULL + ev), ev < 2 ? HALF : HALF + 4096);
            mbar_wait(BAR(B_PUB + 2), 0);
            const uint32_t* fp = g_flag + (2 + (lane >> 3)) * 128 + 8 * r + (lane & 7);
            const uint32_t* src = g_ox + (size_t)2 * r * 14336;
            const float2* ssrc = g_st + 2 * r * 512;
#pragma unroll 1
            for (int n = 0, ev = 0; ev < 4; n++) {
                if (ev == 1) mbar_wait(BAR(B_PUB + 3), 0);
                uint32_t ok = __ballot_sync(~0u, (int)(ld_relaxed(fp) - target) >= 0) >> (8 * ev);
                while ((ok & 0xFFu) == 0xFFu) {
                    asm volatile("fence.acquire.gpu;" ::: "memory");
                    fence_async_global();
                    const uint32_t bar = BAR(B_GFULL + ev);
                    bulk_e(sb + (ev == 0 ? OFF_X : OFF_Y + (ev & 1) * HALF), src + (ev >> 1) * (34 * 14336) + (ev & 1) * 14336, HALF, bar);
                    if (ev >= 2) bulk_e(sb + OFF_X + X_STAT + (ev & 1) * 4096, ssrc + (ev & 1) * 512, 4096, bar);
                    if (ev) PROFH(4 + ev);
                    ev++; ok >>= 8;
                }
                if (n > SPIN_LIMIT) __trap();
            }
#pragma unroll 1
            for (int ps = 0; ps < 3; ps++) {
                mbar_wait(BAR(B_PUB + 6 + ps), 0);
                if (lane < 4) wait_flag(g_flag + (6 + ps) * 128 + 8 * r + 2 * lane + kh, target);
                warp_arrive(BAR(B_HRDY + ps));
                PROFH(9 + ps);
            }
        } else {
            if (lane == 0) {
#pragma unroll 1
                for (int k = 0; k < 9; k++) {
                    mbar_wait(BAR(B_PUB + k), 0);
                    fence_gpu();
                    st_relaxed(g_flag + k * 128 + b, target);
                    if (k >= 3 && k <= 5) PROFH1(k - 3);
                }
            }
        }
    }
}

typedef CUresult (*EncodeFn)(CUtensorMap*, CUtensorMapDataType, cuuint32_t, void*, const cuuint64_t*, const cuuint64_t*, const cuuint32_t*,
                             const cuuint32_t*, CUtensorMapInterleave, CUtensorMapSwizzle, CUtensorMapL2promotion, CUtensorMapFloatOOBfill);

static void make_map(EncodeFn fn, CUtensorMap* m, const void* ptr, uint64_t d0, uint64_t d1, uint64_t d2, uint64_t s1, uint64_t s2,
                     uint32_t b0, uint32_t b1, uint32_t b2, CUtensorMapSwizzle sw) {
    cuuint64_t dims[3] = {d0, d1, d2}, strides[2] = {s1, s2};
    cuuint32_t box[3] = {b0, b1, b2}, es[3] = {1, 1, 1};
    CUresult rc = fn(m, CU_TENSOR_MAP_DATA_TYPE_BFLOAT16, 3, (void*)ptr, dims, strides, box, es, CU_TENSOR_MAP_INTERLEAVE_NONE, sw,
                     CU_TENSOR_MAP_L2_PROMOTION_L2_128B, CU_TENSOR_MAP_FLOAT_OOB_FILL_NONE);
    (void)rc;
}

extern "C" void kernel_launch(void* const* d_in, const int* in_sizes, int n_in, void* d_out, int out_size) {
    (void)in_sizes; (void)n_in; (void)out_size;
    static EncodeFn fn = nullptr;
    if (!fn) {
        cudaDriverEntryPointQueryResult st;
        cudaGetDriverEntryPoint("cuTensorMapEncodeTiled", (void**)&fn, cudaEnableDefault, &st);
        cudaFuncSetAttribute(fused_block_kernel, cudaFuncAttributeMaxDynamicSharedMemorySize, SMEM_BYTES);
    }
    Params p;
    p.x = (const bf16*)d_in[0];
    const bf16* wqkv = (const bf16*)d_in[1];
    p.wqkv = wqkv;
    p.wop = (const bf16*)d_in[2];
    p.wg = (const bf16*)d_in[4];
    p.wu = (const bf16*)d_in[5];
    p.wd = (const bf16*)d_in[6];
    p.c = (const bf16*)d_in[7];
    p.wmod = (const bf16*)d_in[8];
    p.out = (bf16*)d_out;
    p.zero = 0;
    make_map(fn, &p.wm, p.wmod, 2688, 448, 1, 5376, 5376 * 448, 16, 224, 1, CU_TENSOR_MAP_SWIZZLE_NONE);
    make_map(fn, &p.xm, p.x, 448, 2048, 1, 896, 896 * 2048, 64, 128, 1, CU_TENSOR_MAP_SWIZZLE_128B);
    make_map(fn, &p.qkv, wqkv, 1344, 448, 1, 2688, 2688 * 448, 64, 224, 1, CU_TENSOR_MAP_SWIZZLE_128B);
    make_map(fn, &p.wo, p.wop, 448, 448, 1, 896, 896 * 448, 64, 224, 1, CU_TENSOR_MAP_SWIZZLE_128B);
    make_map(fn, &p.ga, p.wg, 64, 448, 28, 3584, 128, 64, 32, 2, CU_TENSOR_MAP_SWIZZLE_128B);
    make_map(fn, &p.ua, p.wu, 64, 448, 28, 3584, 128, 64, 32, 2, CU_TENSOR_MAP_SWIZZLE_128B);
    make_map(fn, &p.gb, p.wg, 64, 448, 28, 3584, 128, 64, 64, 1, CU_TENSOR_MAP_SWIZZLE_128B);
    make_map(fn, &p.ub, p.wu, 64, 448, 28, 3584, 128, 64, 64, 1, CU_TENSOR_MAP_SWIZZLE_128B);
    make_map(fn, &p.gc, p.wg, 32, 448, 56, 3584, 64, 32, 64, 1, CU_TENSOR_MAP_SWIZZLE_64B);
    make_map(fn, &p.uc, p.wu, 32, 448, 56, 3584, 64, 32, 64, 1, CU_TENSOR_MAP_SWIZZLE_64B);
    make_map(fn, &p.dn, p.wd, 448, 1792, 1, 896, 896 * 1792, 64, 32, 1, CU_TENSOR_MAP_SWIZZLE_128B);
    fused_block_kernel<<<GRID, 384, SMEM_BYTES>>>(p);
}
```

```cpp
#include <cuda_runtime.h>
#include <cuda_bf16.h>
#include <cuda.h>
#include <stdint.h>

typedef __nv_bfloat16 bf16;

template<int TB> __device__ __forceinline__ void wgmma_rs_56(float* d, uint32_t a0, uint32_t a1, uint32_t a2, uint32_t a3, uint64_t db, int sd) {
  asm volatile("{\n.reg .pred p;\nsetp.ne.b32 p, %33, 0;\n"
    "wgmma.mma_async.sync.aligned.m64n56k16.f32.bf16.bf16 {%0,%1,%2,%3,%4,%5,%6,%7,%8,%9,%10,%11,%12,%13,%14,%15,%16,%17,%18,%19,%20,%21,%22,%23,%24,%25,%26,%27}, {%28,%29,%30,%31}, %32, p, 1, 1, %34;\n}\n"
    : "+f"(d[0]),"+f"(d[1]),"+f"(d[2]),"+f"(d[3]),"+f"(d[4]),"+f"(d[5]),"+f"(d[6]),"+f"(d[7]),"+f"(d[8]),"+f"(d[9]),"+f"(d[10]),"+f"(d[11]),"+f"(d[12]),"+f"(d[13]),"+f"(d[14]),"+f"(d[15]),"+f"(d[16]),"+f"(d[17]),"+f"(d[18]),"+f"(d[19]),"+f"(d[20]),"+f"(d[21]),"+f"(d[22]),"+f"(d[23]),"+f"(d[24]),"+f"(d[25]),"+f"(d[26]),"+f"(d[27])
    : "r"(a0), "r"(a1), "r"(a2), "r"(a3), "l"(db), "r"(sd), "n"(TB));
}
template<int TB> __device__ __forceinline__ void wgmma_ss_56(float* d, uint64_t da, uint64_t db, int sd) {
  asm volatile("{\n.reg .pred p;\nsetp.ne.b32 p, %30, 0;\n"
    "wgmma.mma_async.sync.aligned.m64n56k16.f32.bf16.bf16 {%0,%1,%2,%3,%4,%5,%6,%7,%8,%9,%10,%11,%12,%13,%14,%15,%16,%17,%18,%19,%20,%21,%22,%23,%24,%25,%26,%27}, %28, %29, p, 1, 1, 0, %31;\n}\n"
    : "+f"(d[0]),"+f"(d[1]),"+f"(d[2]),"+f"(d[3]),"+f"(d[4]),"+f"(d[5]),"+f"(d[6]),"+f"(d[7]),"+f"(d[8]),"+f"(d[9]),"+f"(d[10]),"+f"(d[11]),"+f"(d[12]),"+f"(d[13]),"+f"(d[14]),"+f"(d[15]),"+f"(d[16]),"+f"(d[17]),"+f"(d[18]),"+f"(d[19]),"+f"(d[20]),"+f"(d[21]),"+f"(d[22]),"+f"(d[23]),"+f"(d[24]),"+f"(d[25]),"+f"(d[26]),"+f"(d[27])
    : "l"(da), "l"(db), "r"(sd), "n"(TB));
}
template<int TB> __device__ __forceinline__ void wgmma_rs_256(float* d, uint32_t a0, uint32_t a1, uint32_t a2, uint32_t a3, uint64_t db, int sd) {
  asm volatile("{\n.reg .pred p;\nsetp.ne.b32 p, %133, 0;\n"
    "wgmma.mma_async.sync.aligned.m64n256k16.f32.bf16.bf16 {%0,%1,%2,%3,%4,%5,%6,%7,%8,%9,%10,%11,%12,%13,%14,%15,%16,%17,%18,%19,%20,%21,%22,%23,%24,%25,%26,%27,%28,%29,%30,%31,%32,%33,%34,%35,%36,%37,%38,%39,%40,%41,%42,%43,%44,%45,%46,%47,%48,%49,%50,%51,%52,%53,%54,%55,%56,%57,%58,%59,%60,%61,%62,%63,%64,%65,%66,%67,%68,%69,%70,%71,%72,%73,%74,%75,%76,%77,%78,%79,%80,%81,%82,%83,%84,%85,%86,%87,%88,%89,%90,%91,%92,%93,%94,%95,%96,%97,%98,%99,%100,%101,%102,%103,%104,%105,%106,%107,%108,%109,%110,%111,%112,%113,%114,%115,%116,%117,%118,%119,%120,%121,%122,%123,%124,%125,%126,%127}, {%128,%129,%130,%131}, %132, p, 1, 1, %134;\n}\n"
    : "+f"(d[0]),"+f"(d[1]),"+f"(d[2]),"+f"(d[3]),"+f"(d[4]),"+f"(d[5]),"+f"(d[6]),"+f"(d[7]),"+f"(d[8]),"+f"(d[9]),"+f"(d[10]),"+f"(d[11]),"+f"(d[12]),"+f"(d[13]),"+f"(d[14]),"+f"(d[15]),"+f"(d[16]),"+f"(d[17]),"+f"(d[18]),"+f"(d[19]),"+f"(d[20]),"+f"(d[21]),"+f"(d[22]),"+f"(d[23]),"+f"(d[24]),"+f"(d[25]),"+f"(d[26]),"+f"(d[27]),"+f"(d[28]),"+f"(d[29]),"+f"(d[30]),"+f"(d[31]),"+f"(d[32]),"+f"(d[33]),"+f"(d[34]),"+f"(d[35]),"+f"(d[36]),"+f"(d[37]),"+f"(d[38]),"+f"(d[39]),"+f"(d[40]),"+f"(d[41]),"+f"(d[42]),"+f"(d[43]),"+f"(d[44]),"+f"(d[45]),"+f"(d[46]),"+f"(d[47]),"+f"(d[48]),"+f"(d[49]),"+f"(d[50]),"+f"(d[51]),"+f"(d[52]),"+f"(d[53]),"+f"(d[54]),"+f"(d[55]),"+f"(d[56]),"+f"(d[57]),"+f"(d[58]),"+f"(d[59]),"+f"(d[60]),"+f"(d[61]),"+f"(d[62]),"+f"(d[63]),"+f"(d[64]),"+f"(d[65]),"+f"(d[66]),"+f"(d[67]),"+f"(d[68]),"+f"(d[69]),"+f"(d[70]),"+f"(d[71]),"+f"(d[72]),"+f"(d[73]),"+f"(d[74]),"+f"(d[75]),"+f"(d[76]),"+f"(d[77]),"+f"(d[78]),"+f"(d[79]),"+f"(d[80]),"+f"(d[81]),"+f"(d[82]),"+f"(d[83]),"+f"(d[84]),"+f"(d[85]),"+f"(d[86]),"+f"(d[87]),"+f"(d[88]),"+f"(d[89]),"+f"(d[90]),"+f"(d[91]),"+f"(d[92]),"+f"(d[93]),"+f"(d[94]),"+f"(d[95]),"+f"(d[96]),"+f"(d[97]),"+f"(d[98]),"+f"(d[99]),"+f"(d[100]),"+f"(d[101]),"+f"(d[102]),"+f"(d[103]),"+f"(d[104]),"+f"(d[105]),"+f"(d[106]),"+f"(d[107]),"+f"(d[108]),"+f"(d[109]),"+f"(d[110]),"+f"(d[111]),"+f"(d[112]),"+f"(d[113]),"+f"(d[114]),"+f"(d[115]),"+f"(d[116]),"+f"(d[117]),"+f"(d[118]),"+f"(d[119]),"+f"(d[120]),"+f"(d[121]),"+f"(d[122]),"+f"(d[123]),"+f"(d[124]),"+f"(d[125]),"+f"(d[126]),"+f"(d[127])
    : "r"(a0), "r"(a1), "r"(a2), "r"(a3), "l"(db), "r"(sd), "n"(TB));
}
template<int TB> __device__ __forceinline__ void wgmma_ss_128(float* d, uint64_t da, uint64_t db, int sd) {
  asm volatile("{\n.reg .pred p;\nsetp.ne.b32 p, %66, 0;\n"
    "wgmma.mma_async.sync.aligned.m64n128k16.f32.bf16.bf16 {%0,%1,%2,%3,%4,%5,%6,%7,%8,%9,%10,%11,%12,%13,%14,%15,%16,%17,%18,%19,%20,%21,%22,%23,%24,%25,%26,%27,%28,%29,%30,%31,%32,%33,%34,%35,%36,%37,%38,%39,%40,%41,%42,%43,%44,%45,%46,%47,%48,%49,%50,%51,%52,%53,%54,%55,%56,%57,%58,%59,%60,%61,%62,%63}, %64, %65, p, 1, 1, 0, %67;\n}\n"
    : "+f"(d[0]),"+f"(d[1]),"+f"(d[2]),"+f"(d[3]),"+f"(d[4]),"+f"(d[5]),"+f"(d[6]),"+f"(d[7]),"+f"(d[8]),"+f"(d[9]),"+f"(d[10]),"+f"(d[11]),"+f"(d[12]),"+f"(d[13]),"+f"(d[14]),"+f"(d[15]),"+f"(d[16]),"+f"(d[17]),"+f"(d[18]),"+f"(d[19]),"+f"(d[20]),"+f"(d[21]),"+f"(d[22]),"+f"(d[23]),"+f"(d[24]),"+f"(d[25]),"+f"(d[26]),"+f"(d[27]),"+f"(d[28]),"+f"(d[29]),"+f"(d[30]),"+f"(d[31]),"+f"(d[32]),"+f"(d[33]),"+f"(d[34]),"+f"(d[35]),"+f"(d[36]),"+f"(d[37]),"+f"(d[38]),"+f"(d[39]),"+f"(d[40]),"+f"(d[41]),"+f"(d[42]),"+f"(d[43]),"+f"(d[44]),"+f"(d[45]),"+f"(d[46]),"+f"(d[47]),"+f"(d[48]),"+f"(d[49]),"+f"(d[50]),"+f"(d[51]),"+f"(d[52]),"+f"(d[53]),"+f"(d[54]),"+f"(d[55]),"+f"(d[56]),"+f"(d[57]),"+f"(d[58]),"+f"(d[59]),"+f"(d[60]),"+f"(d[61]),"+f"(d[62]),"+f"(d[63])
    : "l"(da), "l"(db), "r"(sd), "n"(TB));
}
template<int TB> __device__ __forceinline__ void wgmma_ss_64(float* d, uint64_t da, uint64_t db, int sd) {
  asm volatile("{\n.reg .pred p;\nsetp.ne.b32 p, %34, 0;\n"
    "wgmma.mma_async.sync.aligned.m64n64k16.f32.bf16.bf16 {%0,%1,%2,%3,%4,%5,%6,%7,%8,%9,%10,%11,%12,%13,%14,%15,%16,%17,%18,%19,%20,%21,%22,%23,%24,%25,%26,%27,%28,%29,%30,%31}, %32, %33, p, 1, 1, 0, %35;\n}\n"
    : "+f"(d[0]),"+f"(d[1]),"+f"(d[2]),"+f"(d[3]),"+f"(d[4]),"+f"(d[5]),"+f"(d[6]),"+f"(d[7]),"+f"(d[8]),"+f"(d[9]),"+f"(d[10]),"+f"(d[11]),"+f"(d[12]),"+f"(d[13]),"+f"(d[14]),"+f"(d[15]),"+f"(d[16]),"+f"(d[17]),"+f"(d[18]),"+f"(d[19]),"+f"(d[20]),"+f"(d[21]),"+f"(d[22]),"+f"(d[23]),"+f"(d[24]),"+f"(d[25]),"+f"(d[26]),"+f"(d[27]),"+f"(d[28]),"+f"(d[29]),"+f"(d[30]),"+f"(d[31])
    : "l"(da), "l"(db), "r"(sd), "n"(TB));
}
template<int TB> __device__ __forceinline__ void wgmma_ss_112(float* d, uint64_t da, uint64_t db, int sd) {
  asm volatile("{\n.reg .pred p;\nsetp.ne.b32 p, %58, 0;\n"
    "wgmma.mma_async.sync.aligned.m64n112k16.f32.bf16.bf16 {%0,%1,%2,%3,%4,%5,%6,%7,%8,%9,%10,%11,%12,%13,%14,%15,%16,%17,%18,%19,%20,%21,%22,%23,%24,%25,%26,%27,%28,%29,%30,%31,%32,%33,%34,%35,%36,%37,%38,%39,%40,%41,%42,%43,%44,%45,%46,%47,%48,%49,%50,%51,%52,%53,%54,%55}, %56, %57, p, 1, 1, 0, %59;\n}\n"
    : "+f"(d[0]),"+f"(d[1]),"+f"(d[2]),"+f"(d[3]),"+f"(d[4]),"+f"(d[5]),"+f"(d[6]),"+f"(d[7]),"+f"(d[8]),"+f"(d[9]),"+f"(d[10]),"+f"(d[11]),"+f"(d[12]),"+f"(d[13]),"+f"(d[14]),"+f"(d[15]),"+f"(d[16]),"+f"(d[17]),"+f"(d[18]),"+f"(d[19]),"+f"(d[20]),"+f"(d[21]),"+f"(d[22]),"+f"(d[23]),"+f"(d[24]),"+f"(d[25]),"+f"(d[26]),"+f"(d[27]),"+f"(d[28]),"+f"(d[29]),"+f"(d[30]),"+f"(d[31]),"+f"(d[32]),"+f"(d[33]),"+f"(d[34]),"+f"(d[35]),"+f"(d[36]),"+f"(d[37]),"+f"(d[38]),"+f"(d[39]),"+f"(d[40]),"+f"(d[41]),"+f"(d[42]),"+f"(d[43]),"+f"(d[44]),"+f"(d[45]),"+f"(d[46]),"+f"(d[47]),"+f"(d[48]),"+f"(d[49]),"+f"(d[50]),"+f"(d[51]),"+f"(d[52]),"+f"(d[53]),"+f"(d[54]),"+f"(d[55])
    : "l"(da), "l"(db), "r"(sd), "n"(TB));
}
template<int TB> __device__ __forceinline__ void wgmma_rs_112(float* d, uint32_t a0, uint32_t a1, uint32_t a2, uint32_t a3, uint64_t db, int sd) {
  asm volatile("{\n.reg .pred p;\nsetp.ne.b32 p, %61, 0;\n"
    "wgmma.mma_async.sync.aligned.m64n112k16.f32.bf16.bf16 {%0,%1,%2,%3,%4,%5,%6,%7,%8,%9,%10,%11,%12,%13,%14,%15,%16,%17,%18,%19,%20,%21,%22,%23,%24,%25,%26,%27,%28,%29,%30,%31,%32,%33,%34,%35,%36,%37,%38,%39,%40,%41,%42,%43,%44,%45,%46,%47,%48,%49,%50,%51,%52,%53,%54,%55}, {%56,%57,%58,%59}, %60, p, 1, 1, %62;\n}\n"
    : "+f"(d[0]),"+f"(d[1]),"+f"(d[2]),"+f"(d[3]),"+f"(d[4]),"+f"(d[5]),"+f"(d[6]),"+f"(d[7]),"+f"(d[8]),"+f"(d[9]),"+f"(d[10]),"+f"(d[11]),"+f"(d[12]),"+f"(d[13]),"+f"(d[14]),"+f"(d[15]),"+f"(d[16]),"+f"(d[17]),"+f"(d[18]),"+f"(d[19]),"+f"(d[20]),"+f"(d[21]),"+f"(d[22]),"+f"(d[23]),"+f"(d[24]),"+f"(d[25]),"+f"(d[26]),"+f"(d[27]),"+f"(d[28]),"+f"(d[29]),"+f"(d[30]),"+f"(d[31]),"+f"(d[32]),"+f"(d[33]),"+f"(d[34]),"+f"(d[35]),"+f"(d[36]),"+f"(d[37]),"+f"(d[38]),"+f"(d[39]),"+f"(d[40]),"+f"(d[41]),"+f"(d[42]),"+f"(d[43]),"+f"(d[44]),"+f"(d[45]),"+f"(d[46]),"+f"(d[47]),"+f"(d[48]),"+f"(d[49]),"+f"(d[50]),"+f"(d[51]),"+f"(d[52]),"+f"(d[53]),"+f"(d[54]),"+f"(d[55])
    : "r"(a0), "r"(a1), "r"(a2), "r"(a3), "l"(db), "r"(sd), "n"(TB));
}

constexpr int DM = 448;
constexpr int NCTA = 128;
#define MAPPING 1
#define GRID 132
#define PINGPONG 0
#define WIN 4
#define WIN_END 25
#define UNR_G2 21
#define UNR_B 7
#define UNR_C 7
constexpr int kG2 = UNR_G2, kB = UNR_B, kC = UNR_C;
#define MAP_S 4
constexpr int SPIN_LIMIT = 1 << 22;

constexpr uint32_t OFF_X = 0, OFF_Y = 114688, OFF_MISC = 229376, SMEM_BYTES = 232448;
constexpr uint32_t Y_VR = 0, Y_K = 28672, Y_KOWN = 57344, Y_VOWN = 71680, Y_Q = 86016;
constexpr uint32_t HALF = 57344;
constexpr uint32_t M_BAR = OFF_MISC;
constexpr uint32_t M_ST = OFF_MISC + 512;
constexpr uint32_t M_G = OFF_MISC + 2304;
constexpr uint32_t M_EPOCH = OFF_MISC + 3040;
constexpr uint32_t M_ONCE = OFF_MISC + 3048;
enum { B_XFULL = 0, B_FULLK = 7, B_FULLV = 8, B_FULLQ, B_KRFULL, B_VRFULL, B_WOFULL, B_XCH, B_FULL = 16, B_MOD1 = 28, B_MOD2, B_WMFULL,
       B_EMPTY = 32, B_XFREE = B_EMPTY + 12, B_GEMV, B_PEER,
       B_PUB = 47,
       B_WMFREE = 56, B_HRDY, B_GFULL = B_HRDY + 3, B_DONE = 31 };
constexpr uint32_t X_STAT = 49152;

__device__ uint32_t g_ticket;
__device__ __align__(128) uint32_t g_mod[8 * 6 * DM];
__device__ __align__(128) uint32_t g_flag[9 * 16 * 8];
__device__ __align__(128) uint32_t g_kv[17 * 8 * 2 * 3584];
__device__ __align__(128) uint32_t g_ox[2 * 34 * 14336];
#define g_o g_ox
#define g_x1 (g_ox + 34 * 14336)
__device__ __align__(128) float2 g_st[34 * 8 * 64];
__device__ __align__(128) uint32_t g_h2[17 * 224 * 512];
#define PROFH(id)
#define PROFH1(id)
#define PROFC(id)

struct alignas(64) Params {
    CUtensorMap wm, xm, qkv, wo, ga, ua, gb, ub, gc, uc, dn;
    const bf16 *x, *c, *wqkv, *wmod, *wg, *wu, *wd, *wop;
    bf16* out;
    uint32_t zero;
};

__device__ __forceinline__ void mbar_init(uint32_t bar, int cnt) { asm volatile("mbarrier.init.shared::cta.b64 [%0], %1;" ::"r"(bar), "r"(cnt) : "memory"); }
__device__ __forceinline__ void mbar_expect_tx(uint32_t bar, uint32_t bytes) { asm volatile("mbarrier.arrive.expect_tx.shared::cta.b64 _, [%0], %1;" ::"r"(bar), "r"(bytes) : "memory"); }
__device__ __forceinline__ void mbar_arrive(uint32_t bar) { asm volatile("mbarrier.arrive.shared::cta.b64 _, [%0];" ::"r"(bar) : "memory"); }
__device__ __forceinline__ void mbar_wait(uint32_t bar, uint32_t parity) {
    uint32_t ok; int n = 0;
    do {
        asm volatile("{\n.reg .pred p;\nmbarrier.try_wait.parity.shared::cta.b64 p, [%1], %2;\nselp.u32 %0, 1, 0, p;\n}" : "=r"(ok) : "r"(bar), "r"(parity) : "memory");
        if (++n > SPIN_LIMIT) __trap();
    } while (!ok);
}
__device__ __forceinline__ void mbar_wait_c(uint32_t bar, uint32_t parity) {
    asm volatile("{\n.reg .pred p;\nWL:\nmbarrier.try_wait.parity.shared::cta.b64 p, [%0], %1;\n@!p bra WL;\n}" ::"r"(bar), "r"(parity) : "memory");
}
__device__ __forceinline__ void mbar_wait_cluster(uint32_t bar, uint32_t parity) {
    uint32_t ok; int n = 0;
    do {
        asm volatile("{\n.reg .pred p;\nmbarrier.try_wait.parity.acquire.cluster.shared::cta.b64 p, [%1], %2;\nselp.u32 %0, 1, 0, p;\n}" : "=r"(ok) : "r"(bar), "r"(parity) : "memory");
        if (++n > SPIN_LIMIT) __trap();
    } while (!ok);
}
__device__ __forceinline__ void warp_arrive(uint32_t bar) {
    __syncwarp();
    asm volatile("{\n.reg .pred p;\nelect.sync _|p, 0xffffffff;\n@p mbarrier.arrive.shared::cta.b64 _, [%0];\n}" ::"r"(bar) : "memory");
}
__device__ __forceinline__ int opaque(int v) { return __shfl_sync(~0u, v, 0); }
__device__ __forceinline__ int fresh_tid() { int v; asm volatile("mov.u32 %0, %%tid.x;" : "=r"(v)); return v; }
__device__ __forceinline__ void bar_sync(int id, int n) { asm volatile("bar.sync %0, %1;" ::"r"(id), "r"(n) : "memory"); }
__device__ __forceinline__ void bar_arrive(int id, int n) { asm volatile("bar.arrive %0, %1;" ::"r"(id), "r"(n) : "memory"); }
__device__ __forceinline__ void fence_async_smem() { asm volatile("fence.proxy.async.shared::cta;" ::: "memory"); }
__device__ __forceinline__ void fence_async_global() { asm volatile("fence.proxy.async.global;" ::: "memory"); }
__device__ __forceinline__ void fence_gpu() { asm volatile("fence.release.gpu;" ::: "memory"); }
__device__ __forceinline__ void tma3(uint32_t dst, const CUtensorMap* m, int c0, int c1, int c2, uint32_t bar) {
    asm volatile("cp.async.bulk.tensor.3d.shared::cluster.global.mbarrier::complete_tx::bytes [%0], [%1, {%3, %4, %5}], [%2];"
                 ::"r"(dst), "l"(m), "r"(bar), "r"(c0), "r"(c1), "r"(c2) : "memory");
}
__device__ __forceinline__ void bulk_load(uint32_t dst, const void* src, uint32_t bytes, uint32_t bar) {
    asm volatile("cp.async.bulk.shared::cluster.global.mbarrier::complete_tx::bytes [%0], [%1], %2, [%3];" ::"r"(dst), "l"(src), "r"(bytes), "r"(bar) : "memory");
}
__device__ __forceinline__ void expect_e(uint32_t bar, uint32_t bytes) {
    asm volatile("{\n.reg .pred p;\nelect.sync _|p, 0xffffffff;\n@p mbarrier.arrive.expect_tx.shared::cta.b64 _, [%0], %1;\n}" ::"r"(bar), "r"(bytes) : "memory");
}
__device__ __forceinline__ void tma3_e(uint32_t dst, const CUtensorMap* m, int c0, int c1, int c2, uint32_t bar) {
    asm volatile("{\n.reg .pred p;\nelect.sync _|p, 0xffffffff;\n@p cp.async.bulk.tensor.3d.shared::cluster.global.mbarrier::complete_tx::bytes [%0], [%1, {%3, %4, %5}], [%2];\n}"
                 ::"r"(dst), "l"(m), "r"(bar), "r"(c0), "r"(c1), "r"(c2) : "memory");
}
__device__ __forceinline__ void bulk_e(uint32_t dst, const void* src, uint32_t bytes, uint32_t bar) {
    asm volatile("{\n.reg .pred p;\nelect.sync _|p, 0xffffffff;\n@p cp.async.bulk.shared::cluster.global.mbarrier::complete_tx::bytes [%0], [%1], %2, [%3];\n}"
                 ::"r"(dst), "l"(src), "r"(bytes), "r"(bar) : "memory");
}
__device__ __forceinline__ void init_e(uint32_t bar, int cnt) {
    asm volatile("{\n.reg .pred p;\nelect.sync _|p, 0xffffffff;\n@p mbarrier.init.shared::cta.b64 [%0], %1;\n}" ::"r"(bar), "r"(cnt) : "memory");
}
__device__ __forceinline__ void l2_prefetch_e(const void* src, uint32_t bytes) {
    asm volatile("{\n.reg .pred p;\nelect.sync _|p, 0xffffffff;\n@p cp.async.bulk.prefetch.L2.global [%0], %1;\n}" ::"l"(src), "r"(bytes) : "memory");
}
__device__ __forceinline__ uint32_t ld_relaxed(const uint32_t* p) { uint32_t v; asm volatile("ld.relaxed.gpu.global.u32 %0, [%1];" : "=r"(v) : "l"(p) : "memory"); return v; }
__device__ __forceinline__ void st_relaxed(uint32_t* p, uint32_t v) { asm volatile("st.relaxed.gpu.global.u32 [%0], %1;" ::"l"(p), "r"(v) : "memory"); }
__device__ __forceinline__ uint4 ld_relaxed4(const uint4* p) { uint4 v; asm volatile("ld.relaxed.gpu.global.v4.u32 {%0,%1,%2,%3}, [%4];" : "=r"(v.x), "=r"(v.y), "=r"(v.z), "=r"(v.w) : "l"(p) : "memory"); return v; }
__device__ __forceinline__ void st_relaxed4(uint4* p, uint4 v) { asm volatile("st.relaxed.gpu.global.v4.u32 [%0], {%1,%2,%3,%4};" ::"l"(p), "r"(v.x), "r"(v.y), "r"(v.z), "r"(v.w) : "memory"); }
__device__ __forceinline__ uint4 ldg_nc4(const void* p) { uint4 v; asm volatile("ld.global.nc.L1::no_allocate.v4.u32 {%0,%1,%2,%3}, [%4];" : "=r"(v.x), "=r"(v.y), "=r"(v.z), "=r"(v.w) : "l"(p)); return v; }
__device__ __forceinline__ uint32_t ldg_nc(const void* p) { uint32_t v; asm volatile("ld.global.nc.u32 %0, [%1];" : "=r"(v) : "l"(p)); return v; }
__device__ __forceinline__ uint32_t ld_acquire(const uint32_t* p) { uint32_t v; asm volatile("ld.acquire.gpu.global.u32 %0, [%1];" : "=r"(v) : "l"(p) : "memory"); return v; }
__device__ __forceinline__ uint4 lds4(uint32_t a) { uint4 v; asm volatile("ld.shared.v4.u32 {%0,%1,%2,%3}, [%4];" : "=r"(v.x), "=r"(v.y), "=r"(v.z), "=r"(v.w) : "r"(a) : "memory"); return v; }
__device__ __forceinline__ float2 lds2f(uint32_t a) { float2 v; asm volatile("ld.shared.v2.f32 {%0,%1}, [%2];" : "=f"(v.x), "=f"(v.y) : "r"(a) : "memory"); return v; }
__device__ __forceinline__ uint32_t lds1(uint32_t a) { uint32_t v; asm volatile("ld.shared.u32 %0, [%1];" : "=r"(v) : "r"(a) : "memory"); return v; }
__device__ __forceinline__ void sts4(uint32_t a, uint4 v) { asm volatile("st.shared.v4.u32 [%0], {%1,%2,%3,%4};" ::"r"(a), "r"(v.x), "r"(v.y), "r"(v.z), "r"(v.w) : "memory"); }
__device__ __forceinline__ void sts2(uint32_t a, uint32_t x, uint32_t y) { asm volatile("st.shared.v2.u32 [%0], {%1,%2};" ::"r"(a), "r"(x), "r"(y) : "memory"); }
__device__ __forceinline__ void sts1(uint32_t a, uint32_t v) { asm volatile("st.shared.u32 [%0], %1;" ::"r"(a), "r"(v) : "memory"); }
__device__ __forceinline__ void stsm4(uint32_t a, uint32_t r0, uint32_t r1, uint32_t r2, uint32_t r3) {
    asm volatile("stmatrix.sync.aligned.m8n8.x4.shared.b16 [%0], {%1,%2,%3,%4};" ::"r"(a), "r"(r0), "r"(r1), "r"(r2), "r"(r3));
}
__device__ __forceinline__ uint32_t pack2(float lo, float hi) { uint32_t r; asm("cvt.rn.bf16x2.f32 %0, %1, %2;" : "=r"(r) : "f"(hi), "f"(lo)); return r; }
__device__ __forceinline__ uint32_t pack2_relu(float lo, float hi) { uint32_t r; asm("cvt.rn.relu.bf16x2.f32 %0, %1, %2;" : "=r"(r) : "f"(hi), "f"(lo)); return r; }
__device__ __forceinline__ uint32_t hfma2(uint32_t a, uint32_t b, uint32_t c) { uint32_t r; asm("fma.rn.bf16x2 %0, %1, %2, %3;" : "=r"(r) : "r"(a), "r"(b), "r"(c)); return r; }
__device__ __forceinline__ uint32_t hmul2(uint32_t a, uint32_t b) { uint32_t r; asm("mul.rn.bf16x2 %0, %1, %2;" : "=r"(r) : "r"(a), "r"(b)); return r; }
__device__ __forceinline__ float bf_lo(uint32_t v) { return __uint_as_float(v << 16); }
__device__ __forceinline__ float bf_hi(uint32_t v) { return __uint_as_float(v & 0xFFFF0000u); }
__device__ __forceinline__ float bf_round(float v) { return bf_lo(pack2(v, 0.f)); }
__device__ __forceinline__ float ex2(float x) { float r; asm("ex2.approx.ftz.f32 %0, %1;" : "=f"(r) : "f"(x)); return r; }
__device__ __forceinline__ void mma16816(float* d, uint32_t a0, uint32_t a1, uint32_t a2, uint32_t a3, uint32_t b0, uint32_t b1) {
    asm("mma.sync.aligned.m16n8k16.row.col.f32.bf16.bf16.f32 {%0,%1,%2,%3}, {%4,%5,%6,%7}, {%8,%9}, {%0,%1,%2,%3};"
        : "+f"(d[0]), "+f"(d[1]), "+f"(d[2]), "+f"(d[3]) : "r"(a0), "r"(a1), "r"(a2), "r"(a3), "r"(b0), "r"(b1));
}
__device__ __forceinline__ void mma16816_first(float* d, uint32_t a0, uint32_t a1, uint32_t a2, uint32_t a3, uint32_t b0, uint32_t b1) {
    asm volatile("mma.sync.aligned.m16n8k16.row.col.f32.bf16.bf16.f32 {%0,%1,%2,%3}, {%4,%5,%6,%7}, {%8,%9}, {%10,%10,%10,%10};"
        : "=f"(d[0]), "=f"(d[1]), "=f"(d[2]), "=f"(d[3]) : "r"(a0), "r"(a1), "r"(a2), "r"(a3), "r"(b0), "r"(b1), "f"(0.f));
}
__device__ __forceinline__ void mma16816_v(float* d, uint32_t a0, uint32_t a1, uint32_t a2, uint32_t a3, uint32_t b0, uint32_t b1) {
    asm volatile("mma.sync.aligned.m16n8k16.row.col.f32.bf16.bf16.f32 {%0,%1,%2,%3}, {%4,%5,%6,%7}, {%8,%9}, {%0,%1,%2,%3};"
        : "+f"(d[0]), "+f"(d[1]), "+f"(d[2]), "+f"(d[3]) : "r"(a0), "r"(a1), "r"(a2), "r"(a3), "r"(b0), "r"(b1));
}
__device__ __forceinline__ void mma1688(float* d, uint32_t a0, uint32_t a1, uint32_t b0) {
    asm("mma.sync.aligned.m16n8k8.row.col.f32.bf16.bf16.f32 {%0,%1,%2,%3}, {%4,%5}, {%6}, {%0,%1,%2,%3};"
        : "+f"(d[0]), "+f"(d[1]), "+f"(d[2]), "+f"(d[3]) : "r"(a0), "r"(a1), "r"(b0));
}
__device__ __forceinline__ void ldsm4(uint32_t a, uint32_t* r) {
    asm volatile("ldmatrix.sync.aligned.m8n8.x4.shared.b16 {%0,%1,%2,%3}, [%4];" : "=r"(r[0]), "=r"(r[1]), "=r"(r[2]), "=r"(r[3]) : "r"(a));
}
__device__ __forceinline__ void ldsm4t(uint32_t a, uint32_t* r) {
    asm volatile("ldmatrix.sync.aligned.m8n8.x4.trans.shared.b16 {%0,%1,%2,%3}, [%4];" : "=r"(r[0]), "=r"(r[1]), "=r"(r[2]), "=r"(r[3]) : "r"(a));
}
__device__ __forceinline__ float rcp(float x) { float r; asm("rcp.approx.ftz.f32 %0, %1;" : "=f"(r) : "f"(x)); return r; }
__device__ __forceinline__ uint2 ld_relaxed2(const void* p) { uint2 v; asm volatile("ld.relaxed.gpu.global.v2.u32 {%0,%1}, [%2];" : "=r"(v.x), "=r"(v.y) : "l"(p) : "memory"); return v; }
__device__ __forceinline__ void st_relaxed2(void* p, uint32_t x, uint32_t y) { asm volatile("st.relaxed.gpu.global.v2.u32 [%0], {%1,%2};" ::"l"(p), "r"(max(x, 1u)), "r"(max(y, 1u)) : "memory"); }
__device__ __forceinline__ constexpr uint64_t dconst(uint32_t lbo, uint32_t sbo, uint32_t swz) {
    return ((uint64_t)(lbo >> 4) << 16) | ((uint64_t)(sbo >> 4) << 32) | ((uint64_t)swz << 62);
}
__device__ __forceinline__ uint64_t mkdesc(uint32_t addr, uint64_t c) { return c | (uint64_t)((addr & 0x3FFFF) >> 4); }
#define WG_FENCE() asm volatile("wgmma.fence.sync.aligned;" ::: "memory")
#define WG_COMMIT() asm volatile("wgmma.commit_group.sync.aligned;" ::: "memory")
#define WG_WAIT(n) asm volatile("wgmma.wait_group.sync.aligned %0;" ::"n"(n) : "memory")
template <int N> __device__ __forceinline__ void reg_fence(float* d) {
#pragma unroll
    for (int i = 0; i < N; i++) asm volatile("" : "+f"(d[i])::"memory");
}
template <int N> __device__ __forceinline__ void reg_def(float* d) {
#pragma unroll
    for (int i = 0; i < N; i++) asm volatile("" : "=f"(d[i]));
}
template <int N> __device__ __forceinline__ void reg_def(uint32_t* d) {
#pragma unroll
    for (int i = 0; i < N; i++) asm volatile("" : "=r"(d[i]));
}
__device__ __forceinline__ bool is_unset(uint4 v) { return min(min(v.x, v.y), min(v.z, v.w)) == 0u; }
__device__ __forceinline__ uint4 nz4(uint32_t a, uint32_t b, uint32_t c, uint32_t d) { return make_uint4(max(a, 1u), max(b, 1u), max(c, 1u), max(d, 1u)); }
__device__ __forceinline__ void wait_flag(const uint32_t* p, uint32_t target) {
    int n = 0;
    while ((int)(ld_relaxed(p) - target) < 0) { if (++n > SPIN_LIMIT) __trap(); }
    asm volatile("fence.acquire.gpu;" ::: "memory");
}
__device__ __forceinline__ float silu_bf(uint32_t cbits) {
    const float c = __uint_as_float(cbits << 16);
    return bf_round(__fdividef(c, 1.f + fminf(ex2(-1.4426950408889634f * c), 1e30f)));
}
__device__ __forceinline__ void gemv_part(uint32_t wmbuf, int npanel, int wp, int lane) {
    const uint32_t wa = wmbuf + wp * 512 + (8 * (lane >> 4) + (lane & 7)) * 32 + ((lane >> 3) & 1) * 16;
    uint2 B[4];
#pragma unroll
    for (int i = 0; i < 4; i++) { const float2 v = lds2f(wmbuf + 28672 + (wp + 8 * i) * 32 + (lane & 3) * 8); B[i] = make_uint2(__float_as_uint(v.x), __float_as_uint(v.y)); }
#pragma unroll 1
    for (int pn = 0; pn < npanel; pn++) {
        float d[4] = {};
        uint32_t A[16];
#pragma unroll
        for (int i = 0; i < 4; i++) ldsm4t(wa + pn * 14336 + (i < 3 || wp < 4 ? i : 0) * 4096, A + 4 * i);
#pragma unroll
        for (int i = 0; i < 4; i++) mma16816(d, A[4 * i], A[4 * i + 1], A[4 * i + 2], A[4 * i + 3], B[i].x, B[i].y);
        if ((lane & 3) == 0) {
            sts1(wmbuf + 29696 + (wp * 32 + pn * 16 + (lane >> 2)) * 4, __float_as_uint(d[0]));
            sts1(wmbuf + 29696 + (wp * 32 + pn * 16 + 8 + (lane >> 2)) * 4, __float_as_uint(d[2]));
        }
    }
}
__device__ __forceinline__ void gather_poll(uint32_t sb, int ev, int r, int wi, int lane) {
    const uint32_t target = lds1(sb + M_EPOCH) + 1;
    const uint32_t* fp = g_flag + (2 + ev) * 128 + 8 * r + (lane & 7);
    const uint32_t t0 = clock();
    while (clock() - t0 < wi * 180u) {}
    while (!__all_sync(~0u, (int)(ld_relaxed(fp) - target) >= 0)) {}
    uint32_t first = 0;
    if (lane == 0) asm volatile("atom.shared.exch.b32 %0, [%1], 1;" : "=r"(first) : "r"(sb + M_ONCE + 4 * ev) : "memory");
    if (__shfl_sync(~0u, first, 0) == 0) {
        asm volatile("fence.acquire.gpu;" ::: "memory");
        fence_async_global();
        const uint32_t bar = sb + M_BAR + 8 * (B_GFULL + ev);
        bulk_e(sb + OFF_Y + (ev & 1) * HALF, g_ox + (size_t)((ev >> 1) * 34 + 2 * r + (ev & 1)) * 14336, HALF, bar);
        if (ev >= 2) bulk_e(sb + OFF_X + X_STAT + (ev & 1) * 4096, g_st + (2 * r + (ev & 1)) * 512, 4096, bar);
        PROFH(4 + ev);
    }
}
__device__ __forceinline__ int pass_f(int fs, int ps) { return 224 * fs + ((fs & 1) ? (ps == 0 ? 96 : ps == 1 ? 32 : 0) : (ps == 0 ? 0 : ps == 1 ? 128 : 192)); }
__device__ __forceinline__ constexpr uint32_t slot_off(int l) { return (l < 3 || l > 6 ? l : l == 6 ? 3 : l + 1) * 16384; }
__device__ __forceinline__ void ln_coeffs(float mean, float msq, uint32_t& r2, uint32_t& n2) {
    const float rs = bf_round(rsqrtf(fmaxf(msq - mean * mean, 0.f) + 1e-5f));
    r2 = pack2(rs, rs);
    n2 = pack2(-mean * rs, -mean * rs);
}

template <int sec> __device__ __forceinline__ void ring_loader(const Params& p, uint32_t sb_, int r_, int j_) {
    const uint32_t sb = opaque(sb_);
    const int r = opaque(r_), j = opaque(j_), nq = j >> 1, fs = 4 * (j & 1) + nq;
    const int fa = pass_f(fs, 0), fb = pass_f(fs, 1), fc = pass_f(fs, 2);
#define BAR(i) (sb + M_BAR + 8 * (i))
#define kh (j & 1)
            int sl = 0;
#pragma unroll 1
            for (int s = 0; s < 28; s++) {
                if (s >= 1 && s < 6) mbar_wait(BAR(B_FULL + s - 1), 0);
                const int ps = s < 14 ? 0 : s < 21 ? 1 : 2;
                const uint32_t half = ps < 2 ? 8192 : 4096;
                mbar_wait(BAR(B_EMPTY + sl), (s >= 7 && s < 14) || s >= 21);
                expect_e(BAR(B_FULL + sl), half);
                tma3_e(sb + slot_off(sl) + sec * half, &p.ga + 2 * ps + sec, 0, ps ? 64 * sl : 32 * s, ps == 0 ? fa >> 6 : ps == 1 ? fb >> 6 : fc >> 5, BAR(B_FULL + sl));
                sl = sl == 6 ? 0 : sl + 1;
            }
            if (!sec) PROFH(3);
#pragma unroll 1
            for (int e = 0; e < 4; e++) {
                const uint32_t dst = sb + slot_off(e) + sec * 8192, bar = BAR(B_FULL + e);
                const int f = (e < 2 ? fa + 64 * e : e == 2 ? fb : fc) + 32 * sec;
                mbar_wait(BAR(B_EMPTY + e), 0);
                expect_e(bar, e == 3 && sec ? 0 : 8192);
                if (!(e == 3 && sec)) { tma3_e(dst, &p.dn, 112 * nq + 48, f, 0, bar); tma3_e(dst + 4096, &p.dn, 112 * nq, f, 0, bar); }
            }
            sl = 4;
            int e = 4;
#pragma unroll 1
            for (int grp = 0; grp < 9; grp++) {
                const int ps = grp >= 6 ? 2 : grp >= 3 ? 1 : 0;
                int sidx = grp - 3 * ps;
                if (sec && sidx == 0) { mbar_wait(BAR(B_HRDY + ps), 0); fence_async_global(); }
                sidx += sidx >= nq;
                int f = pass_f(4 * kh + sidx, ps);
#pragma unroll 1
                for (int k = 4 >> ps; k > 0; k--, e++, f += 32) {
                    const uint32_t dst = sb + slot_off(sl), bar = BAR(B_FULL + sl);
                    mbar_wait(BAR(B_EMPTY + sl), e >= 12 && e < 24);
                    if (e < WIN_END && e >= WIN) mbar_wait(BAR(B_FULL + (sl >= WIN ? sl - WIN : sl + 12 - WIN)), e - WIN >= 12);
                    expect_e(bar, 8192);
                    if (!sec) { tma3_e(dst, &p.dn, 112 * nq + 48, f, 0, bar); tma3_e(dst + 4096, &p.dn, 112 * nq, f, 0, bar); }
                    else bulk_e(dst + 8192, g_h2 + (size_t)r * (224 * 512) + f * 64, 8192, bar);
                    sl = sl == 11 ? 0 : sl + 1;
                }
            }
            if (!sec) PROFH(4);
}

__global__ void __cluster_dims__(2, 1, 1) __launch_bounds__(384, 1) fused_block_kernel(const __grid_constant__ Params p) {
    extern __shared__ __align__(1024) unsigned char smem[];
    const uint32_t sb = (uint32_t)__cvta_generic_to_shared(smem);
    const int tid = threadIdx.x, lane = tid & 31, warp = __shfl_sync(~0u, tid >> 5, 0);
    const int m = blockIdx.x >> 1;
    int r, nq;
    {
        int g, i;
        if (m < MAP_S) { g = m < 4 ? 15 : 16; i = m & 3; }
        else if (m < MAP_S + 32) { g = (m - MAP_S) & 7; i = (m - MAP_S) >> 3; }
        else if (m < MAP_S + 60) { i = (m - MAP_S - 32) / 7; g = 8 + (m - MAP_S - 32) - 7 * i; }
        else { g = 16; i = m & 3; }
        r = g; nq = i;
    }
    const int j = opaque(2 * nq + (blockIdx.x & 1)), b = 8 * r + j, fs = 4 * kh + nq;
    const uint32_t sc = r == 16;
    if (lane == 0 && warp < 9 && warp != 6 && warp != 7) {
        const int i0 = warp == 8 ? 0 : 8 + 8 * warp, cnt = warp == 0 || warp == 8 ? 1 : warp < 3 ? 2 : 8;
#pragma unroll
        for (int k = 0; k < 8; k++) if (i0 + k != B_WMFULL) mbar_init(BAR(i0 + k), cnt);
        asm volatile("fence.mbarrier_init.release.cluster;" ::: "memory");
        fence_async_smem();
    }

    if (warp < 8) {
        const int w = warp >> 2, wi = warp & 3;
#define COORDS const int t = fresh_tid() & 127, lane = t & 31, q = lane & 3, lr = lane >> 2, ra = 64 * w + 16 * wi + lr; \
        const uint32_t lx = (lane >> 4) ^ (lane & 7), mrow = (64 * w + 16 * wi + ((lane >> 3) & 1) * 8 + (lane & 7)) * 128; \
        (void)q; (void)lr; (void)ra; (void)lx; (void)mrow;
        const int sid = 2 * (j & 3) + w;
#define RUN(k) (!sc || sid == (k))
#define WAIT(i, par) mbar_wait_c(BAR(i), (par) | sc)
        constexpr uint64_t DB128 = dconst(4096, 1024, 1);
        bar_arrive(9, 384);
        bar_sync(0, 384);
        asm volatile("barrier.cluster.arrive.relaxed.aligned;" ::: "memory");
        asm volatile("setmaxnreg.inc.sync.aligned.u32 224;");
        PROFC(0);
        uint32_t xr[16];
        {
            COORDS
            uint32_t h[112];
            if (RUN(0)) {
                float ds[4] = {}, da[2][4] = {}, db[2][4] = {};
                const uint32_t ONE2 = 0x3F803F80u;
                if (kh == 0) { WAIT(B_WMFULL, 0); gemv_part(sb + OFF_Y + HALF, 1, warp, lane); warp_arrive(BAR(B_GEMV)); }
#pragma unroll
                for (int kb = 0; kb < 7; kb++) {
                    WAIT(B_XFULL + kb, 0);
#pragma unroll
                    for (int k4 = 0; k4 < 4; k4++) ldsm4(sb + OFF_X + mrow + kb * 16384 + (((2 * k4) ^ lx) << 4), h + 16 * kb + 4 * k4);
#pragma unroll
                    for (int k4 = 0; k4 < 4; k4++) {
                        const uint32_t* f = h + 16 * kb + 4 * k4;
                        mma16816(ds, f[0], f[1], f[2], f[3], ONE2, ONE2);
                        mma1688(da[0], f[0], f[1], f[0]); mma1688(db[0], f[0], f[1], f[1]);
                        mma1688(da[1], f[2], f[3], f[2]); mma1688(db[1], f[2], f[3], f[3]);
                    }
                }
#pragma unroll
                for (int i = 0; i < 4; i++) {
                    const int ch = 7 * j + 2 * i + (lane >> 4);
                    ldsm4(sb + OFF_X + mrow + (ch >> 3) * 16384 + (((ch ^ lane) & 7) << 4), xr + 4 * i);
                }
                warp_arrive(BAR(B_XFREE));
                float qa = (lr & 1) ? da[0][1] + da[1][1] : da[0][0] + da[1][0];
                float qb = (lr & 1) ? db[0][3] + db[1][3] : db[0][2] + db[1][2];
                const int src = (lane & ~3) | (lr >> 1);
                qa = __shfl_sync(~0u, qa, src);
                qb = __shfl_sync(~0u, qb, src);
                uint32_t ra2, na2, rb2, nb2;
                ln_coeffs(ds[0] * (1.f / DM), qa * (1.f / DM), ra2, na2);
                ln_coeffs(ds[2] * (1.f / DM), qb * (1.f / DM), rb2, nb2);
#pragma unroll
                for (int i = 0; i < 112; i += 2) { h[i] = hfma2(h[i], ra2, na2); h[i + 1] = hfma2(h[i + 1], rb2, nb2); }
                if (kh == 1) { WAIT(B_WMFULL, 0); gemv_part(sb + OFF_Y + HALF, 2, warp, lane); warp_arrive(BAR(B_GEMV)); }
            } else { reg_def<112>(h); reg_def<16>(xr); }
            PROFC(1);
            if (RUN(1)) {
                float ak[28], av[28], aq[28];
                uint32_t kp[14], vp[14];
                const uint64_t bk0 = mkdesc(sb + OFF_Y, DB128) + kh, bv0 = mkdesc(sb + OFF_Y + HALF, DB128) + kh, bq0 = mkdesc(sb + OFF_X, DB128) + kh;
                uint32_t* kvg = g_kv + (size_t)(b * 2) * 3584 + (8 * w + 2 * wi) * 224 + lane;
                WAIT(B_FULLK, 0);
                WAIT(B_MOD1, 0);
                PROFC(2);
                reg_def<28>(ak);
#pragma unroll
                for (int g4 = 0; g4 < 4; g4++) {
#pragma unroll
                    for (int ks = 7 * g4; ks < 7 * g4 + 7; ks++) {
                        const uint4 st = *(const uint4*)(smem + M_ST + ks * 64 + q * 16);
                        h[4 * ks] = hfma2(h[4 * ks], st.x, st.y); h[4 * ks + 1] = hfma2(h[4 * ks + 1], st.x, st.y);
                        h[4 * ks + 2] = hfma2(h[4 * ks + 2], st.z, st.w); h[4 * ks + 3] = hfma2(h[4 * ks + 3], st.z, st.w);
                    }
                    WG_FENCE();
#pragma unroll
                    for (int ks = 7 * g4; ks < 7 * g4 + 7; ks++) wgmma_rs_56<1>(ak, h[4 * ks], h[4 * ks + 1], h[4 * ks + 2], h[4 * ks + 3], bk0 + ks * 128, ks != 0);
                }
                WG_COMMIT();
                PROFC(3);
                WAIT(B_FULLV, 0);
                reg_def<28>(av);
                WG_FENCE();
#pragma unroll
                for (int ks = 0; ks < 8; ks++) wgmma_rs_56<1>(av, h[4 * ks], h[4 * ks + 1], h[4 * ks + 2], h[4 * ks + 3], bv0 + ks * 128, ks != 0);
                WG_COMMIT();
                WG_WAIT(1);
                reg_fence<28>(ak);
#pragma unroll
                for (int g = 0; g < 7; g++) {
                    kp[2 * g] = pack2(ak[4 * g], ak[4 * g + 1]); kp[2 * g + 1] = pack2(ak[4 * g + 2], ak[4 * g + 3]);
                    kvg[g * 32] = kp[2 * g]; kvg[224 + g * 32] = kp[2 * g + 1];
                }
                warp_arrive(BAR(B_PUB));
                PROFC(4);
                WG_FENCE();
#pragma unroll
                for (int ks = 8; ks < 28; ks++) wgmma_rs_56<1>(av, h[4 * ks], h[4 * ks + 1], h[4 * ks + 2], h[4 * ks + 3], bv0 + ks * 128, 1);
                WG_COMMIT();
                WAIT(B_FULLQ, 0);
                reg_def<28>(aq);
                WG_FENCE();
#pragma unroll
                for (int ks = 0; ks < 8; ks++) wgmma_rs_56<1>(aq, h[4 * ks], h[4 * ks + 1], h[4 * ks + 2], h[4 * ks + 3], bq0 + ks * 128, ks != 0);
                WG_COMMIT();
                WG_WAIT(1);
                reg_fence<28>(av);
#pragma unroll
                for (int g = 0; g < 7; g++) {
                    vp[2 * g] = pack2(av[4 * g], av[4 * g + 1]); vp[2 * g + 1] = pack2(av[4 * g + 2], av[4 * g + 3]);
                    kvg[3584 + g * 32] = vp[2 * g]; kvg[3584 + 224 + g * 32] = vp[2 * g + 1];
                }
                warp_arrive(BAR(B_PUB + 1));
                PROFC(5);
                WG_FENCE();
#pragma unroll
                for (int ks = 8; ks < 28; ks++) wgmma_rs_56<1>(aq, h[4 * ks], h[4 * ks + 1], h[4 * ks + 2], h[4 * ks + 3], bq0 + ks * 128, 1);
                WG_COMMIT();
                WAIT(B_PUB + 1, 0);
                const uint32_t ko = sb + OFF_Y + Y_KOWN + (8 * w + 2 * wi) * 896 + lane * 4;
                const uint32_t qo = sb + OFF_Y + Y_Q + (8 * w + 2 * wi) * 1024 + lane * 4;
#pragma unroll
                for (int g = 0; g < 7; g++) {
                    sts1(ko + g * 128, kp[2 * g]); sts1(ko + 896 + g * 128, kp[2 * g + 1]);
                    sts1(ko + (Y_VOWN - Y_KOWN) + g * 128, vp[2 * g]); sts1(ko + (Y_VOWN - Y_KOWN) + 896 + g * 128, vp[2 * g + 1]);
                }
                WG_WAIT(0);
                reg_fence<28>(aq);
                __syncwarp();
                if (lane < 3 && w == 1) mbar_arrive(BAR(B_EMPTY + lane));
#pragma unroll
                for (int g = 0; g < 7; g++) {
                    const uint32_t q0 = pack2(aq[4 * g], aq[4 * g + 1]), q1 = pack2(aq[4 * g + 2], aq[4 * g + 3]);
                    if (g == 3) {
                        sts1(qo + 3 * 128, q < 2 ? q0 : 0u); sts1(qo + 1024 + 3 * 128, q < 2 ? q1 : 0u);
                        sts1(qo + 4 * 128, q < 2 ? 0u : q0); sts1(qo + 1024 + 4 * 128, q < 2 ? 0u : q1);
                    } else {
                        const int ch = g < 3 ? g : g + 1;
                        sts1(qo + ch * 128, q0); sts1(qo + 1024 + ch * 128, q1);
                    }
                }
                if (!sc) bar_sync(3, 256);
            }
        }
        PROFC(6);
        WAIT(B_KRFULL, 0);
        PROFC(7);
        if (RUN(2)) {
#pragma unroll 1
            for (int hf = sc; hf < 2; hf++) {
                COORDS
                float s[136];
                float na = 0.f, nb = 0.f;
                const float CS = 0.18898223650461361f * 1.4426950408889634f;
                const int kg0 = 8 * hf + 2 * wi;
                const int pmin = 16 - 8 * r - 4 * hf - wi;
                const float NEG = __int_as_float(0xFF800000);
                {
                    uint32_t F[8];
                    const uint32_t qa = sb + OFF_Y + Y_Q + (kg0 + ((lane >> 3) & 1)) * 1024 + (4 * w + (lane >> 4)) * 128 + (lane & 7) * 16;
                    ldsm4(qa, F); ldsm4(qa + 256, F + 4);
                    uint32_t ka = sb + OFF_Y + Y_K + kg0 * 896 + (3 * w + (lane >> 3)) * 128 + (lane & 7) * 16;
#pragma unroll
                    for (int g = 0; g < 34; g++) {
                        uint32_t B[4];
                        if (g >= 12 && g % 4 == 0) ka += __float_as_uint(s[4 * (g - 12)]) & p.zero;
                        ldsm4(ka + g * 896, B);
                        mma16816_first(s + 4 * g, F[0], F[1], F[2], F[3], B[0], B[1]);
                        mma16816_v(s + 4 * g, F[4], F[5], F[6], F[7], B[2], B[3]);
                    }
                    const bool c0 = 2 * q > lr, c1 = 2 * q + 1 > lr;
                    if (!c0) { s[0] = NEG; s[6] = NEG; }
                    if (!c1) { s[1] = NEG; s[7] = NEG; }
                    s[2] = NEG; s[3] = NEG;
                    if (c0) { s[128] = NEG; s[134] = NEG; }
                    if (c1) { s[129] = NEG; s[135] = NEG; }
                    s[132] = NEG; s[133] = NEG;
                    float ma = NEG, mb = NEG;
#pragma unroll
                    for (int pp = 0; pp < 17; pp++) {
                        const float* e = s + 8 * pp;
                        const float bias = pp < pmin ? NEG : 0.f;
                        ma = fmaxf(ma, fmaxf(fmaxf(e[0], e[1]), fmaxf(e[4], e[5])) + bias);
                        mb = fmaxf(mb, fmaxf(fmaxf(e[2], e[3]), fmaxf(e[6], e[7])) + bias);
                    }
                    ma = fmaxf(ma, __shfl_xor_sync(~0u, ma, 1)); mb = fmaxf(mb, __shfl_xor_sync(~0u, mb, 1));
                    ma = fmaxf(ma, __shfl_xor_sync(~0u, ma, 2)); mb = fmaxf(mb, __shfl_xor_sync(~0u, mb, 2));
                    na = -ma * CS; nb = -mb * CS;
                }
                PROFC(8 + 3 * hf);
                {
                    WAIT(B_VRFULL, 0);
                    float o[16] = {}, rs[4] = {};
                    uint32_t pk[2];
                    const uint32_t va = sb + OFF_Y + Y_VR + (kg0 + ((lane >> 3) & 1)) * 896 + (3 * w + (lane >> 4)) * 128 + (lane & 7) * 16;
#pragma unroll
                    for (int pp = 0; pp < 17; pp++) {
                        uint32_t B[8];
                        const uint32_t v = va + pp * 1792 + (pp == 16 || (pp >= 9 && kg0 + 2 * pp >= 32) ? Y_VOWN - 32 * 896 : 0);
                        ldsm4t(v, B); ldsm4t(v + 256, B + 4);
                        float e[8];
                        const float bias = __uint_as_float((pp < pmin ? 0xFF800000u : 0u) | ((pp < 2 ? B[0] : pk[pp & 1]) & p.zero));
#pragma unroll
                        for (int i = 0; i < 8; i++) e[i] = ex2(fmaf(s[8 * pp + i], CS, ((i & 2) ? nb : na) + bias));
                        const uint32_t p0 = pack2(e[0], e[1]), p1 = pack2(e[2], e[3]), p2 = pack2(e[4], e[5]), p3 = pack2(e[6], e[7]);
                        pk[pp & 1] = p3;
                        mma16816(rs, p0, p1, p2, p3, 0x3F803F80u, 0x3F803F80u);
#pragma unroll
                        for (int g = 0; g < 4; g++) mma16816(o + 4 * g, p0, p1, p2, p3, B[2 * g], B[2 * g + 1]);
                    }
                    PROFC(9 + 3 * hf);
                    const float ia = rcp(rs[0]), ib = rcp(rs[2]);
                    uint32_t* og = g_o + (size_t)(2 * r + hf) * 14336 + (7 * j + 3 * w) * 256 + wi * 64 + lane;
#pragma unroll
                    for (int g = 0; g < 4; g++) {
                        if ((g == 3 - 3 * w) ? ((q >> 1) == w) : true) {
                            og[g * 256] = pack2(o[4 * g] * ia, o[4 * g + 1] * ia);
                            og[g * 256 + 32] = pack2(o[4 * g + 2] * ib, o[4 * g + 3] * ib);
                        }
                    }
                    warp_arrive(BAR(B_PUB + 2 + hf));
                    PROFC(10 + 3 * hf);
                }
            }
        }
        uint32_t x1p[14];
        COORDS
        constexpr uint64_t DT = dconst(1024, 128, 0);
        if (RUN(4)) {
            float ac[28];
            const uint64_t ad = mkdesc(sb + (w ? OFF_Y + HALF : OFF_X), DT), bd = mkdesc(sb + OFF_X + HALF, DB128) + kh;
            WAIT(B_WOFULL, 0);
            WAIT(B_MOD2, 0);
            if (w == 1 && !sc) gather_poll(sb, 1, r, wi, lane);
            WAIT(B_GFULL + w, 0);
            PROFC(28);
            reg_def<28>(ac);
#pragma unroll 1
            for (int u = 0; u < 4; u++) {
                WG_FENCE();
#pragma unroll
                for (int i = 0; i < 7; i++) wgmma_ss_56<1>(ac, ad + (7 * u + i) * 128, bd + (7 * u + i) * 128, (u | i) != 0);
            }
            WG_COMMIT();
            WG_WAIT(0);
            reg_fence<28>(ac);
            PROFC(14);
            __syncwarp();
            if (lane < 3) mbar_arrive(BAR(B_EMPTY + 3 + lane));
            if (lane < 3 && w == 0) mbar_arrive(BAR(B_EMPTY + lane));
            float s1a = 0.f, s2a = 0.f, s1b = 0.f, s2b = 0.f;
            uint32_t* xo = g_x1 + (size_t)(2 * r + w) * 14336 + 7 * j * 256 + wi * 64 + lane;
#pragma unroll
            for (int g = 0; g < 7; g++) {
                const float2 ga = *(const float2*)(smem + M_G + (8 * g + 2 * q) * 4);
                x1p[2 * g] = pack2(fmaf(ga.x, ac[4 * g], bf_lo(xr[2 * g])), fmaf(ga.y, ac[4 * g + 1], bf_hi(xr[2 * g])));
                x1p[2 * g + 1] = pack2(fmaf(ga.x, ac[4 * g + 2], bf_lo(xr[2 * g + 1])), fmaf(ga.y, ac[4 * g + 3], bf_hi(xr[2 * g + 1])));
                xo[g * 256] = x1p[2 * g]; xo[g * 256 + 32] = x1p[2 * g + 1];
                const float u0 = bf_lo(x1p[2 * g]), u1 = bf_hi(x1p[2 * g]), u2 = bf_lo(x1p[2 * g + 1]), u3 = bf_hi(x1p[2 * g + 1]);
                s1a += u0 + u1; s2a += u0 * u0 + u1 * u1; s1b += u2 + u3; s2b += u2 * u2 + u3 * u3;
            }
            float ka = (q & 1) ? s2a : s1a, kb2 = (q & 1) ? s2b : s1b;
            ka += __shfl_xor_sync(~0u, (q & 1) ? s1a : s2a, 1); kb2 += __shfl_xor_sync(~0u, (q & 1) ? s1b : s2b, 1);
            const float kk = ((q & 2) ? kb2 : ka) + __shfl_xor_sync(~0u, (q & 2) ? ka : kb2, 2);
            ((float*)g_st)[(((2 * r + w) * 8 + j) * 64 + 16 * wi + lr + 4 * (q & 2)) * 2 + (q & 1)] = kk;
            __syncwarp();
            if (lane < 2) mbar_arrive(BAR(B_PUB + 4 + w));
        } else reg_def<14>(x1p);
        PROFC(15);
        uint32_t h2a[32], h2b[24];
        if (RUN(6)) {
            const int fa = pass_f(fs, 0), fb = pass_f(fs, 1), fc = pass_f(fs, 2);
            uint32_t* h2g = g_h2 + (size_t)r * (224 * 512) + (8 * w + 2 * wi) * 32 + lane;
            const uint64_t a0 = mkdesc(sb + OFF_Y + w * HALF, DT);
            {
                WAIT(B_PUB + 3 + w, 0);
                if (!sc) gather_poll(sb, 2 + w, r, wi, lane);
                WAIT(B_GFULL + 2 + w, 0);
                PROFC(16);
                float2 sa = make_float2(0.f, 0.f), sbb = sa;
#pragma unroll
                for (int jj = 0; jj < 8; jj++) {
                    const float2 u = lds2f(sb + OFF_X + X_STAT + w * 4096 + (jj * 64 + 16 * wi + lr) * 8), v = lds2f(sb + OFF_X + X_STAT + w * 4096 + (jj * 64 + 16 * wi + lr + 8) * 8);
                    sa.x += u.x; sa.y += u.y; sbb.x += v.x; sbb.y += v.y;
                }
                warp_arrive(BAR(B_EMPTY + 6));
                uint32_t ra2, na2, rb2, nb2;
                ln_coeffs(sa.x * (1.f / DM), sa.y * (1.f / DM), ra2, na2);
                ln_coeffs(sbb.x * (1.f / DM), sbb.y * (1.f / DM), rb2, nb2);
                const uint32_t ha = sb + OFF_Y + w * HALF + (lane >> 4) * 1024 + (2 * wi + ((lane >> 3) & 1)) * 128 + (lane & 7) * 16;
                const uint32_t sta = sb + M_ST + q * 16;
                auto prep = [&](int s, uint32_t* f) {
                    uint32_t x[8];
                    ldsm4(ha + s * 4096, x); ldsm4(ha + s * 4096 + 2048, x + 4);
                    const uint4 st[2] = {lds4(sta + s * 128), lds4(sta + s * 128 + 64)};
#pragma unroll
                    for (int i = 0; i < 2; i++) {
                        f[4 * i] = hfma2(hfma2(x[4 * i], ra2, na2), st[i].x, st[i].y); f[4 * i + 1] = hfma2(hfma2(x[4 * i + 1], rb2, nb2), st[i].x, st[i].y);
                        f[4 * i + 2] = hfma2(hfma2(x[4 * i + 2], ra2, na2), st[i].z, st[i].w); f[4 * i + 3] = hfma2(hfma2(x[4 * i + 3], rb2, nb2), st[i].z, st[i].w);
                    }
                    stsm4(ha + s * 4096, f[0], f[1], f[2], f[3]); stsm4(ha + s * 4096 + 2048, f[4], f[5], f[6], f[7]);
                };
                float ac[128];
                uint32_t fr[3][8];
                const uint64_t bx = mkdesc(sb, DB128);
                reg_def<128>(ac);
                prep(0, fr[0]);
                PROFC(17);
#pragma unroll
                for (int s = 0; s < 14; s++) {
                    const uint32_t* f = fr[s % 3];
                    const uint64_t bd = bx + (slot_off(s % 7) >> 4);
                    WAIT(B_FULL + s % 7, s >= 7);
                    WG_FENCE();
                    wgmma_rs_256<1>(ac, f[0], f[1], f[2], f[3], bd, s != 0);
                    wgmma_rs_256<1>(ac, f[4], f[5], f[6], f[7], bd + 128, 1);
                    WG_COMMIT();
                    if (s < 13) prep(s + 1, fr[(s + 1) % 3]);
                    if (s > 0) { WG_WAIT(1); warp_arrive(BAR(B_EMPTY + (s - 1) % 7)); }
                }
                PROFC(18);
                fence_async_smem();
                WG_WAIT(0);
                reg_fence<128>(ac);
                warp_arrive(BAR(B_EMPTY + 6));
#pragma unroll
                for (int g = 0; g < 16; g++) {
                    h2a[2 * g] = hmul2(pack2_relu(ac[4 * g], ac[4 * g + 1]), pack2(ac[64 + 4 * g], ac[64 + 4 * g + 1]));
                    h2a[2 * g + 1] = hmul2(pack2_relu(ac[4 * g + 2], ac[4 * g + 3]), pack2(ac[64 + 4 * g + 2], ac[64 + 4 * g + 3]));
                    h2g[(fa / 8 + g) * 512] = h2a[2 * g]; h2g[(fa / 8 + g) * 512 + 32] = h2a[2 * g + 1];
                }
                warp_arrive(BAR(B_PUB + 6));
                bar_sync(1 + w, 128);
            }
            PROFC(19);
            {
                float ac[64];
                reg_def<64>(ac);
                const uint64_t bx = mkdesc(sb, dconst(8192, 1024, 1));
#pragma unroll kB
                for (int s = 0; s < 7; s++) {
                    WAIT(B_FULL + s, 0);
                    const uint64_t ad = a0 + s * 512, bd = bx + (slot_off(s) >> 4);
                    WG_FENCE();
#pragma unroll
                    for (int k = 0; k < 4; k++) wgmma_ss_128<1>(ac, ad + k * 128, bd + k * 128, (s | k) != 0);
                    WG_COMMIT();
                    if (s > 0) { WG_WAIT(1); warp_arrive(BAR(B_EMPTY + s - 1)); }
                }
                WG_WAIT(0);
                reg_fence<64>(ac);
                warp_arrive(BAR(B_EMPTY + 6));
#pragma unroll
                for (int g = 0; g < 8; g++) {
                    h2b[2 * g] = hmul2(pack2_relu(ac[4 * g], ac[4 * g + 1]), pack2(ac[32 + 4 * g], ac[32 + 4 * g + 1]));
                    h2b[2 * g + 1] = hmul2(pack2_relu(ac[4 * g + 2], ac[4 * g + 3]), pack2(ac[32 + 4 * g + 2], ac[32 + 4 * g + 3]));
                    h2g[(fb / 8 + g) * 512] = h2b[2 * g]; h2g[(fb / 8 + g) * 512 + 32] = h2b[2 * g + 1];
                }
                warp_arrive(BAR(B_PUB + 7));
            }
            PROFC(27);
            {
                float ac[32];
                reg_def<32>(ac);
                const uint64_t bx = mkdesc(sb, dconst(4096, 512, 2));
#pragma unroll kC
                for (int s = 0; s < 7; s++) {
                    WAIT(B_FULL + s, 1);
                    const uint64_t ad = a0 + p.zero + s * 512, bd = bx + (slot_off(s) >> 4);
                    WG_FENCE();
#pragma unroll
                    for (int k = 0; k < 4; k++) wgmma_ss_64<1>(ac, ad + k * 128, bd + k * 64, (s | k) != 0);
                    WG_COMMIT();
                    if (s > 0) { WG_WAIT(1); warp_arrive(BAR(B_EMPTY + s - 1)); }
                }
                WG_WAIT(0);
                reg_fence<32>(ac);
                __syncwarp();
                if (lane < 6) mbar_arrive(BAR(B_EMPTY + 6 + lane));
                PROFC(20);
#pragma unroll
                for (int g = 0; g < 4; g++) {
                    h2b[16 + 2 * g] = hmul2(pack2_relu(ac[4 * g], ac[4 * g + 1]), pack2(ac[16 + 4 * g], ac[16 + 4 * g + 1]));
                    h2b[16 + 2 * g + 1] = hmul2(pack2_relu(ac[4 * g + 2], ac[4 * g + 3]), pack2(ac[16 + 4 * g + 2], ac[16 + 4 * g + 3]));
                    h2g[(fc / 8 + g) * 512] = h2b[16 + 2 * g]; h2g[(fc / 8 + g) * 512 + 32] = h2b[16 + 2 * g + 1];
                }
                warp_arrive(BAR(B_PUB + 8));
                asm volatile("barrier.cluster.wait.aligned;" ::: "memory");
                if (lane == 0 && !sc) {
                    uint32_t rb;
                    asm volatile("mapa.shared::cluster.u32 %0, %1, %2;" : "=r"(rb) : "r"(BAR(B_PEER)), "r"(kh ^ 1));
                    asm volatile("mbarrier.arrive.relaxed.cluster.shared::cluster.b64 _, [%0];" ::"r"(rb) : "memory");
                }
            }
        } else { reg_def<32>(h2a); reg_def<24>(h2b); }
        PROFC(21);
        if (RUN(7)) {
            float ac[56];
            reg_def<56>(ac);
            constexpr uint64_t DAN = dconst(2048, 128, 0);
            const uint64_t bx = mkdesc(sb, DB128);
#pragma unroll
            for (int e = 0; e < 4; e++) {
                WAIT(B_FULL + e, 0);
                const uint64_t bd = bx + (slot_off(e) >> 4);
                const uint32_t* hh = e < 2 ? h2a + 16 * e : h2b + 16 * (e - 2);
                WG_FENCE();
#pragma unroll
                for (int k = 0; k < (e < 3 ? 4 : 2); k++) wgmma_rs_112<1>(ac, hh[4 * k], hh[4 * k + 1], hh[4 * k + 2], hh[4 * k + 3], bd + (k >> 1) * 512 + (k & 1) * 128, (e | k) != 0);
                WG_COMMIT();
                if (e > 0) { WG_WAIT(1); warp_arrive(BAR(B_EMPTY + e - 1)); }
            }
            PROFC(22);
            const uint64_t ax = mkdesc(sb + 8192 + w * 1024, DAN);
#pragma unroll kG2
            for (int e = 4; e < 25; e++) {
                WAIT(B_FULL + e % 12, e >= 12 && e < 24);
                if (e == 16) PROFC(23);
                const uint64_t z = (e / 12) * p.zero;
                const uint64_t ad = ax + z + (slot_off(e % 12) >> 4), bd = bx + z + (slot_off(e % 12) >> 4);
                WG_FENCE();
                wgmma_ss_112<1>(ac, ad, bd, 1);
                wgmma_ss_112<1>(ac, ad + 256, bd + 128, 1);
                WG_COMMIT();
                if (e < 14) { WG_WAIT(1); warp_arrive(BAR(B_EMPTY + (e - 1) % 12)); }
            }
            mbar_wait_cluster(BAR(B_PEER), sc);
            WG_WAIT(0);
            reg_fence<56>(ac);
            PROFC(24);
            uint32_t rdst, rbar;
            asm volatile("mapa.shared::cluster.u32 %0, %1, %2;" : "=r"(rdst) : "r"(sb + OFF_Y + (5 + w) * 16384 + t * 16), "r"(kh ^ 1 ^ sc));
            asm volatile("mapa.shared::cluster.u32 %0, %1, %2;" : "=r"(rbar) : "r"(BAR(B_XCH + w)), "r"(kh ^ 1 ^ sc));
#define ACG(g, i) ac[4 * (((g) + 8) % 14) + (i)]
#pragma unroll
            for (int g = 0; g < 7; g++) {
                const float v0 = kh ? ACG(g, 0) : ACG(g + 7, 0), v1 = kh ? ACG(g, 1) : ACG(g + 7, 1);
                const float v2 = kh ? ACG(g, 2) : ACG(g + 7, 2), v3 = kh ? ACG(g, 3) : ACG(g + 7, 3);
                if (!sc) asm volatile("st.async.shared::cluster.mbarrier::complete_tx::bytes.v4.f32 [%0], {%1,%2,%3,%4}, [%5];"
                             ::"r"(rdst + g * 2048), "f"(v0), "f"(v1), "f"(v2), "f"(v3), "r"(rbar) : "memory");
            }
            mbar_wait_cluster(BAR(B_XCH + w), sc);
            PROFC(25);
            bf16* og = (sc ? (bf16*)(g_h2 + 16 * 224 * 512) : p.out + (size_t)128 * r * DM) + (size_t)ra * DM + 56 * j + 2 * q;
#pragma unroll
            for (int g = 0; g < 7; g++) {
                const uint4 rv = *(const uint4*)(smem + OFF_Y + (5 + w) * 16384 + t * 16 + g * 2048);
                const float2 gb = *(const float2*)(smem + M_G + 224 + (8 * g + 2 * q) * 4);
                const float v0 = (kh ? ACG(g + 7, 0) : ACG(g, 0)) + __uint_as_float(rv.x), v1 = (kh ? ACG(g + 7, 1) : ACG(g, 1)) + __uint_as_float(rv.y);
                const float v2 = (kh ? ACG(g + 7, 2) : ACG(g, 2)) + __uint_as_float(rv.z), v3 = (kh ? ACG(g + 7, 3) : ACG(g, 3)) + __uint_as_float(rv.w);
                *(uint32_t*)(og + 8 * g) = pack2(fmaf(gb.x, v0, bf_lo(x1p[2 * g])), fmaf(gb.y, v1, bf_hi(x1p[2 * g])));
                *(uint32_t*)(og + 8 * DM + 8 * g) = pack2(fmaf(gb.x, v2, bf_lo(x1p[2 * g + 1])), fmaf(gb.y, v3, bf_hi(x1p[2 * g + 1])));
            }
        }
        PROFC(26);
        bar_sync(1 + w, 128);
        if (wi == 0) warp_arrive(BAR(B_DONE));
    } else {
        const int lane = fresh_tid() & 31;
        const bool early = kh == 0, gemv = r < 14;
        const int mcol = early ? 16 * (4 * r + nq) : 2 * DM + 32 * (4 * r + nq);
        const uint32_t wmbuf = sb + OFF_Y + HALF;
        asm volatile("setmaxnreg.dec.sync.aligned.u32 56;");
        if (warp == 9) {
#pragma unroll
            for (int i = 56; i < 64; i++) init_e(BAR(i), 1);
            if (lane < 4) sts1(sb + M_ONCE + 4 * lane, 0);
            fence_async_smem();
        }
        if (warp == 8) { init_e(BAR(B_WMFULL), 2); fence_async_smem(); }
        bar_arrive(0, 384);
        asm volatile("barrier.cluster.arrive.relaxed.aligned;" ::: "memory");
        uint32_t target = 0;
        if (warp == 8) {
            if (!sc) {
                expect_e(BAR(B_WMFULL), gemv ? 28672 >> early : 0);
                if (early && gemv) { tma3_e(wmbuf, &p.wm, mcol, 0, 0, BAR(B_WMFULL)); tma3_e(wmbuf + 7168, &p.wm, mcol, 224, 0, BAR(B_WMFULL)); }
#pragma unroll 1
                for (int kb = 0; kb < 7; kb++) {
                    expect_e(BAR(B_XFULL + kb), 16384);
                    tma3_e(sb + OFF_X + kb * 16384, &p.xm, 64 * kb, 128 * r, 0, BAR(B_XFULL + kb));
                }
            }
#pragma unroll 1
            for (int mt = 0; mt < 4; mt++) {
                if (mt == 1) {
                    if (!early && gemv) {
#pragma unroll 1
                        for (int k = 0; k < 4; k++) tma3_e(wmbuf + k * 7168, &p.wm, mcol + (k >> 1) * 16, (k & 1) * 224, 0, BAR(B_WMFULL));
                    }
                    bar_sync(9, 384);
                    if (sc) return;
                    mbar_wait(BAR(B_MOD1), 0);
                    mbar_wait(BAR(B_WMFREE), 0);
                }
                if (mt == 2) mbar_wait(BAR(B_XFREE), 0);
                if (mt == 3) mbar_wait(BAR(B_VRFULL), 0);
                const uint32_t bar = BAR(mt == 3 ? B_WOFULL : B_FULLK + mt), dst = sb + (mt < 2 ? OFF_Y : OFF_X) + (mt & 1) * HALF;
                const int c0 = (mt < 2 ? DM + DM * mt : 0) + 56 * j - 8 * kh;
                if (!sc) {
                    expect_e(bar, HALF);
                    tma3_e(dst, mt == 3 ? &p.wo : &p.qkv, c0, 0, 0, bar);
                    tma3_e(dst + HALF / 2, mt == 3 ? &p.wo : &p.qkv, c0, 224, 0, bar);
                }
            }
            expect_e(BAR(B_XCH), 14336);
            expect_e(BAR(B_XCH + 1), 14336);
        } else {
            if (warp == 10 && !sc) {
                l2_prefetch_e((const char*)p.wqkv + (size_t)b * 9408, 9408);
                if (lane == 0) sts1(sb + M_EPOCH, atomicAdd(&g_ticket, 1u) / NCTA);
            }
            if (warp == 11) {
#pragma unroll
                for (int i = 0; i < 8; i++) {
                    const int wd = lane + 32 * i;
                    const uint32_t cb = i < 7 ? __ldg((const uint32_t*)p.c + wd) : 0u;
                    sts1(wmbuf + 28672 + (wd >> 3) * 32 + (wd & 3) * 8 + (wd & 4), pack2(silu_bf(cb & 0xFFFFu), silu_bf(cb >> 16)));
                }
            }
            bar_sync(9, 384);
            if (sc) return;
            target = lds1(sb + M_EPOCH) + 1;
            const uint32_t tag = target & 0xFFFFu;
            if (warp == 11) {
                warp_arrive(BAR(B_WMFULL));
                mbar_wait(BAR(B_GEMV), 0);
                float sum = 0.f;
#pragma unroll
                for (int i = 0; i < 8; i++) sum += *(const float*)(smem + OFF_Y + HALF + 29696 + (i * 32 + (early ? lane & 15 : lane)) * 4);
                const uint32_t word = (pack2(sum, 0.f) << 16) | tag;
                if (gemv) {
                    uint32_t* mg = g_mod + mcol + (early ? (lane & 15) + (lane >> 4) * 4 * 6 * DM : lane);
#pragma unroll
                    for (int i = 0; i < 8; i++) if (i < 4 || !early) st_relaxed(mg + i * 6 * DM, word);
                }
                warp_arrive(BAR(B_WMFREE));
            }
            const uint4* modp = (const uint4*)g_mod + (r & 7) * (6 * DM / 4);
            const bool p2 = warp == 11;
            mbar_wait(BAR(p2 ? B_PUB : B_XFULL + 4), 0);
#pragma unroll 1
            for (int it = p2 ? 0 : warp - 9; it < (p2 ? 2 : warp - 8); it++) {
                const int i0 = lane + 32 * it, imax = p2 ? 251 : 223;
                uint4 v[4];
#pragma unroll 1
                for (int n = 0;; n++) {
                    uint32_t bad = 0;
#pragma unroll
                    for (int k = 0; k < 4; k++) {
                        const int i = min(i0 + 64 * k, imax);
                        v[k] = ld_relaxed4(modp + (i < 224 ? (p2 ? 336 : 0) + i : (i < 238 ? 14 * j + i : 14 * j + i + 322)));
                        bad |= (v[k].x ^ tag) | (v[k].y ^ tag) | (v[k].z ^ tag) | (v[k].w ^ tag);
                    }
                    if (!__any_sync(~0u, bad & 0xFFFFu)) break;
                    if (n > SPIN_LIMIT) __trap();
                }
#pragma unroll
                for (int k = 0; k < 4; k++) {
                    const int i = min(i0 + 64 * k, imax);
                    if (i < 224) {
                        const int isc = i >= 112, c4 = i - 112 * isc;
                        const float one = isc ? 1.f : 0.f;
                        const uint32_t a = sb + M_ST + (c4 >> 2) * 64 + (c4 & 1) * 32 + (c4 & 2) * 4 + (isc ? 0 : 4);
                        sts1(a, pack2(bf_hi(v[k].x) + one, bf_hi(v[k].y) + one));
                        sts1(a + 16, pack2(bf_hi(v[k].z) + one, bf_hi(v[k].w) + one));
                    } else {
                        sts4(sb + M_G + (i - 224) * 16, make_uint4(v[k].x & 0xFFFF0000u, v[k].y & 0xFFFF0000u, v[k].z & 0xFFFF0000u, v[k].w & 0xFFFF0000u));
                    }
                }
                warp_arrive(BAR(p2 ? B_MOD2 : B_MOD1));
            }
            if (warp == 9) {
#pragma unroll 1
                for (int kv = 0; kv < 2; kv++) {
                    mbar_wait(BAR(B_PUB + kv), 0);
                    if (lane >= 1 && lane <= 2 && r >= lane) wait_flag(g_flag + kv * 128 + b - 8 * lane, target);
                    __syncwarp();
                    fence_async_global();
                    const uint32_t dst = sb + OFF_Y + (kv ? Y_VR : Y_K);
                    expect_e(BAR(B_KRFULL + kv), r >= 2 ? 28672 : r == 1 ? 14336 : 0);
                    if (r >= 2) bulk_e(dst, g_kv + (size_t)((b - 16) * 2 + kv) * 3584, 14336, BAR(B_KRFULL + kv));
                    if (r >= 1) bulk_e(dst + 14336, g_kv + (size_t)((b - 8) * 2 + kv) * 3584, 14336, BAR(B_KRFULL + kv));
                }
            } else if (warp == 11) {
                mbar_wait(BAR(B_VRFULL), 0);
                l2_prefetch_e((const char*)p.wg + (size_t)b * 12544, 12544);
                l2_prefetch_e((const char*)p.wu + (size_t)b * 12544, 12544);
                l2_prefetch_e((const char*)p.wd + (size_t)b * 12544, 12544);
            }
        }
        if (warp == 8 || warp == 11) {
            const int sec = warp == 11;
            if (sec) ring_loader<1>(p, sb, r, j); else ring_loader<0>(p, sb, r, j);
            mbar_wait(BAR(B_DONE), 0);
        } else if (warp == 9) {
#pragma unroll
            for (int ev = 0; ev < 4; ev++) expect_e(BAR(B_GFULL + ev), ev < 2 ? HALF : HALF + 4096);
            mbar_wait(BAR(B_PUB + 2), 0);
            wait_flag(g_flag + 2 * 128 + 8 * r + (lane & 7), target);
            __syncwarp();
            fence_async_global();
            bulk_e(sb + OFF_X, g_ox + (size_t)2 * r * 14336, HALF, BAR(B_GFULL));
#pragma unroll 1
            for (int ps = 0; ps < 3; ps++) {
                mbar_wait(BAR(B_PUB + 6 + ps), 0);
                if (lane < 4) wait_flag(g_flag + (6 + ps) * 128 + 8 * r + 2 * lane + kh, target);
                warp_arrive(BAR(B_HRDY + ps));
                PROFH(9 + ps);
            }
        } else {
            if (lane == 0) {
#pragma unroll 1
                for (int k = 0; k < 9; k++) {
                    mbar_wait(BAR(B_PUB + k), 0);
                    fence_gpu();
                    st_relaxed(g_flag + k * 128 + b, target);
                    if (k >= 3 && k <= 5) PROFH1(k - 3);
                }
            }
        }
    }
}

typedef CUresult (*EncodeFn)(CUtensorMap*, CUtensorMapDataType, cuuint32_t, void*, const cuuint64_t*, const cuuint64_t*, const cuuint32_t*,
                             const cuuint32_t*, CUtensorMapInterleave, CUtensorMapSwizzle, CUtensorMapL2promotion, CUtensorMapFloatOOBfill);

static void make_map(EncodeFn fn, CUtensorMap* m, const void* ptr, uint64_t d0, uint64_t d1, uint64_t d2, uint64_t s1, uint64_t s2,
                     uint32_t b0, uint32_t b1, uint32_t b2, CUtensorMapSwizzle sw) {
    cuuint64_t dims[3] = {d0, d1, d2}, strides[2] = {s1, s2};
    cuuint32_t box[3] = {b0, b1, b2}, es[3] = {1, 1, 1};
    CUresult rc = fn(m, CU_TENSOR_MAP_DATA_TYPE_BFLOAT16, 3, (void*)ptr, dims, strides, box, es, CU_TENSOR_MAP_INTERLEAVE_NONE, sw,
                     CU_TENSOR_MAP_L2_PROMOTION_L2_128B, CU_TENSOR_MAP_FLOAT_OOB_FILL_NONE);
    (void)rc;
}

extern "C" void kernel_launch(void* const* d_in, const int* in_sizes, int n_in, void* d_out, int out_size) {
    (void)in_sizes; (void)n_in; (void)out_size;
    static EncodeFn fn = nullptr;
    if (!fn) {
        cudaDriverEntryPointQueryResult st;
        cudaGetDriverEntryPoint("cuTensorMapEncodeTiled", (void**)&fn, cudaEnableDefault, &st);
        cudaFuncSetAttribute(fused_block_kernel, cudaFuncAttributeMaxDynamicSharedMemorySize, SMEM_BYTES);
    }
    Params p;
    p.x = (const bf16*)d_in[0];
    const bf16* wqkv = (const bf16*)d_in[1];
    p.wqkv = wqkv;
    p.wop = (const bf16*)d_in[2];
    p.wg = (const bf16*)d_in[4];
    p.wu = (const bf16*)d_in[5];
    p.wd = (const bf16*)d_in[6];
    p.c = (const bf16*)d_in[7];
    p.wmod = (const bf16*)d_in[8];
    p.out = (bf16*)d_out;
    p.zero = 0;
    make_map(fn, &p.wm, p.wmod, 2688, 448, 1, 5376, 5376 * 448, 16, 224, 1, CU_TENSOR_MAP_SWIZZLE_NONE);
    make_map(fn, &p.xm, p.x, 448, 2048, 1, 896, 896 * 2048, 64, 128, 1, CU_TENSOR_MAP_SWIZZLE_128B);
    make_map(fn, &p.qkv, wqkv, 1344, 448, 1, 2688, 2688 * 448, 64, 224, 1, CU_TENSOR_MAP_SWIZZLE_128B);
    make_map(fn, &p.wo, p.wop, 448, 448, 1, 896, 896 * 448, 64, 224, 1, CU_TENSOR_MAP_SWIZZLE_128B);
    make_map(fn, &p.ga, p.wg, 64, 448, 28, 3584, 128, 64, 32, 2, CU_TENSOR_MAP_SWIZZLE_128B);
    make_map(fn, &p.ua, p.wu, 64, 448, 28, 3584, 128, 64, 32, 2, CU_TENSOR_MAP_SWIZZLE_128B);
    make_map(fn, &p.gb, p.wg, 64, 448, 28, 3584, 128, 64, 64, 1, CU_TENSOR_MAP_SWIZZLE_128B);
    make_map(fn, &p.ub, p.wu, 64, 448, 28, 3584, 128, 64, 64, 1, CU_TENSOR_MAP_SWIZZLE_128B);
    make_map(fn, &p.gc, p.wg, 32, 448, 56, 3584, 64, 32, 64, 1, CU_TENSOR_MAP_SWIZZLE_64B);
    make_map(fn, &p.uc, p.wu, 32, 448, 56, 3584, 64, 32, 64, 1, CU_TENSOR_MAP_SWIZZLE_64B);
    make_map(fn, &p.dn, p.wd, 448, 1792, 1, 896, 896 * 1792, 64, 32, 1, CU_TENSOR_MAP_SWIZZLE_128B);
    fused_block_kernel<<<GRID, 384, SMEM_BYTES>>>(p);
}
```

```cpp
#include <cuda_runtime.h>
#include <cuda_bf16.h>
#include <cuda.h>
#include <stdint.h>

typedef __nv_bfloat16 bf16;

template<int TB> __device__ __forceinline__ void wgmma_rs_56(float* d, uint32_t a0, uint32_t a1, uint32_t a2, uint32_t a3, uint64_t db, int sd) {
  asm volatile("{\n.reg .pred p;\nsetp.ne.b32 p, %33, 0;\n"
    "wgmma.mma_async.sync.aligned.m64n56k16.f32.bf16.bf16 {%0,%1,%2,%3,%4,%5,%6,%7,%8,%9,%10,%11,%12,%13,%14,%15,%16,%17,%18,%19,%20,%21,%22,%23,%24,%25,%26,%27}, {%28,%29,%30,%31}, %32, p, 1, 1, %34;\n}\n"
    : "+f"(d[0]),"+f"(d[1]),"+f"(d[2]),"+f"(d[3]),"+f"(d[4]),"+f"(d[5]),"+f"(d[6]),"+f"(d[7]),"+f"(d[8]),"+f"(d[9]),"+f"(d[10]),"+f"(d[11]),"+f"(d[12]),"+f"(d[13]),"+f"(d[14]),"+f"(d[15]),"+f"(d[16]),"+f"(d[17]),"+f"(d[18]),"+f"(d[19]),"+f"(d[20]),"+f"(d[21]),"+f"(d[22]),"+f"(d[23]),"+f"(d[24]),"+f"(d[25]),"+f"(d[26]),"+f"(d[27])
    : "r"(a0), "r"(a1), "r"(a2), "r"(a3), "l"(db), "r"(sd), "n"(TB));
}
template<int TB> __device__ __forceinline__ void wgmma_ss_56(float* d, uint64_t da, uint64_t db, int sd) {
  asm volatile("{\n.reg .pred p;\nsetp.ne.b32 p, %30, 0;\n"
    "wgmma.mma_async.sync.aligned.m64n56k16.f32.bf16.bf16 {%0,%1,%2,%3,%4,%5,%6,%7,%8,%9,%10,%11,%12,%13,%14,%15,%16,%17,%18,%19,%20,%21,%22,%23,%24,%25,%26,%27}, %28, %29, p, 1, 1, 0, %31;\n}\n"
    : "+f"(d[0]),"+f"(d[1]),"+f"(d[2]),"+f"(d[3]),"+f"(d[4]),"+f"(d[5]),"+f"(d[6]),"+f"(d[7]),"+f"(d[8]),"+f"(d[9]),"+f"(d[10]),"+f"(d[11]),"+f"(d[12]),"+f"(d[13]),"+f"(d[14]),"+f"(d[15]),"+f"(d[16]),"+f"(d[17]),"+f"(d[18]),"+f"(d[19]),"+f"(d[20]),"+f"(d[21]),"+f"(d[22]),"+f"(d[23]),"+f"(d[24]),"+f"(d[25]),"+f"(d[26]),"+f"(d[27])
    : "l"(da), "l"(db), "r"(sd), "n"(TB));
}
template<int TB> __device__ __forceinline__ void wgmma_rs_256(float* d, uint32_t a0, uint32_t a1, uint32_t a2, uint32_t a3, uint64_t db, int sd) {
  asm volatile("{\n.reg .pred p;\nsetp.ne.b32 p, %133, 0;\n"
    "wgmma.mma_async.sync.aligned.m64n256k16.f32.bf16.bf16 {%0,%1,%2,%3,%4,%5,%6,%7,%8,%9,%10,%11,%12,%13,%14,%15,%16,%17,%18,%19,%20,%21,%22,%23,%24,%25,%26,%27,%28,%29,%30,%31,%32,%33,%34,%35,%36,%37,%38,%39,%40,%41,%42,%43,%44,%45,%46,%47,%48,%49,%50,%51,%52,%53,%54,%55,%56,%57,%58,%59,%60,%61,%62,%63,%64,%65,%66,%67,%68,%69,%70,%71,%72,%73,%74,%75,%76,%77,%78,%79,%80,%81,%82,%83,%84,%85,%86,%87,%88,%89,%90,%91,%92,%93,%94,%95,%96,%97,%98,%99,%100,%101,%102,%103,%104,%105,%106,%107,%108,%109,%110,%111,%112,%113,%114,%115,%116,%117,%118,%119,%120,%121,%122,%123,%124,%125,%126,%127}, {%128,%129,%130,%131}, %132, p, 1, 1, %134;\n}\n"
    : "+f"(d[0]),"+f"(d[1]),"+f"(d[2]),"+f"(d[3]),"+f"(d[4]),"+f"(d[5]),"+f"(d[6]),"+f"(d[7]),"+f"(d[8]),"+f"(d[9]),"+f"(d[10]),"+f"(d[11]),"+f"(d[12]),"+f"(d[13]),"+f"(d[14]),"+f"(d[15]),"+f"(d[16]),"+f"(d[17]),"+f"(d[18]),"+f"(d[19]),"+f"(d[20]),"+f"(d[21]),"+f"(d[22]),"+f"(d[23]),"+f"(d[24]),"+f"(d[25]),"+f"(d[26]),"+f"(d[27]),"+f"(d[28]),"+f"(d[29]),"+f"(d[30]),"+f"(d[31]),"+f"(d[32]),"+f"(d[33]),"+f"(d[34]),"+f"(d[35]),"+f"(d[36]),"+f"(d[37]),"+f"(d[38]),"+f"(d[39]),"+f"(d[40]),"+f"(d[41]),"+f"(d[42]),"+f"(d[43]),"+f"(d[44]),"+f"(d[45]),"+f"(d[46]),"+f"(d[47]),"+f"(d[48]),"+f"(d[49]),"+f"(d[50]),"+f"(d[51]),"+f"(d[52]),"+f"(d[53]),"+f"(d[54]),"+f"(d[55]),"+f"(d[56]),"+f"(d[57]),"+f"(d[58]),"+f"(d[59]),"+f"(d[60]),"+f"(d[61]),"+f"(d[62]),"+f"(d[63]),"+f"(d[64]),"+f"(d[65]),"+f"(d[66]),"+f"(d[67]),"+f"(d[68]),"+f"(d[69]),"+f"(d[70]),"+f"(d[71]),"+f"(d[72]),"+f"(d[73]),"+f"(d[74]),"+f"(d[75]),"+f"(d[76]),"+f"(d[77]),"+f"(d[78]),"+f"(d[79]),"+f"(d[80]),"+f"(d[81]),"+f"(d[82]),"+f"(d[83]),"+f"(d[84]),"+f"(d[85]),"+f"(d[86]),"+f"(d[87]),"+f"(d[88]),"+f"(d[89]),"+f"(d[90]),"+f"(d[91]),"+f"(d[92]),"+f"(d[93]),"+f"(d[94]),"+f"(d[95]),"+f"(d[96]),"+f"(d[97]),"+f"(d[98]),"+f"(d[99]),"+f"(d[100]),"+f"(d[101]),"+f"(d[102]),"+f"(d[103]),"+f"(d[104]),"+f"(d[105]),"+f"(d[106]),"+f"(d[107]),"+f"(d[108]),"+f"(d[109]),"+f"(d[110]),"+f"(d[111]),"+f"(d[112]),"+f"(d[113]),"+f"(d[114]),"+f"(d[115]),"+f"(d[116]),"+f"(d[117]),"+f"(d[118]),"+f"(d[119]),"+f"(d[120]),"+f"(d[121]),"+f"(d[122]),"+f"(d[123]),"+f"(d[124]),"+f"(d[125]),"+f"(d[126]),"+f"(d[127])
    : "r"(a0), "r"(a1), "r"(a2), "r"(a3), "l"(db), "r"(sd), "n"(TB));
}
template<int TB> __device__ __forceinline__ void wgmma_ss_128(float* d, uint64_t da, uint64_t db, int sd) {
  asm volatile("{\n.reg .pred p;\nsetp.ne.b32 p, %66, 0;\n"
    "wgmma.mma_async.sync.aligned.m64n128k16.f32.bf16.bf16 {%0,%1,%2,%3,%4,%5,%6,%7,%8,%9,%10,%11,%12,%13,%14,%15,%16,%17,%18,%19,%20,%21,%22,%23,%24,%25,%26,%27,%28,%29,%30,%31,%32,%33,%34,%35,%36,%37,%38,%39,%40,%41,%42,%43,%44,%45,%46,%47,%48,%49,%50,%51,%52,%53,%54,%55,%56,%57,%58,%59,%60,%61,%62,%63}, %64, %65, p, 1, 1, 0, %67;\n}\n"
    : "+f"(d[0]),"+f"(d[1]),"+f"(d[2]),"+f"(d[3]),"+f"(d[4]),"+f"(d[5]),"+f"(d[6]),"+f"(d[7]),"+f"(d[8]),"+f"(d[9]),"+f"(d[10]),"+f"(d[11]),"+f"(d[12]),"+f"(d[13]),"+f"(d[14]),"+f"(d[15]),"+f"(d[16]),"+f"(d[17]),"+f"(d[18]),"+f"(d[19]),"+f"(d[20]),"+f"(d[21]),"+f"(d[22]),"+f"(d[23]),"+f"(d[24]),"+f"(d[25]),"+f"(d[26]),"+f"(d[27]),"+f"(d[28]),"+f"(d[29]),"+f"(d[30]),"+f"(d[31]),"+f"(d[32]),"+f"(d[33]),"+f"(d[34]),"+f"(d[35]),"+f"(d[36]),"+f"(d[37]),"+f"(d[38]),"+f"(d[39]),"+f"(d[40]),"+f"(d[41]),"+f"(d[42]),"+f"(d[43]),"+f"(d[44]),"+f"(d[45]),"+f"(d[46]),"+f"(d[47]),"+f"(d[48]),"+f"(d[49]),"+f"(d[50]),"+f"(d[51]),"+f"(d[52]),"+f"(d[53]),"+f"(d[54]),"+f"(d[55]),"+f"(d[56]),"+f"(d[57]),"+f"(d[58]),"+f"(d[59]),"+f"(d[60]),"+f"(d[61]),"+f"(d[62]),"+f"(d[63])
    : "l"(da), "l"(db), "r"(sd), "n"(TB));
}
template<int TB> __device__ __forceinline__ void wgmma_ss_64(float* d, uint64_t da, uint64_t db, int sd) {
  asm volatile("{\n.reg .pred p;\nsetp.ne.b32 p, %34, 0;\n"
    "wgmma.mma_async.sync.aligned.m64n64k16.f32.bf16.bf16 {%0,%1,%2,%3,%4,%5,%6,%7,%8,%9,%10,%11,%12,%13,%14,%15,%16,%17,%18,%19,%20,%21,%22,%23,%24,%25,%26,%27,%28,%29,%30,%31}, %32, %33, p, 1, 1, 0, %35;\n}\n"
    : "+f"(d[0]),"+f"(d[1]),"+f"(d[2]),"+f"(d[3]),"+f"(d[4]),"+f"(d[5]),"+f"(d[6]),"+f"(d[7]),"+f"(d[8]),"+f"(d[9]),"+f"(d[10]),"+f"(d[11]),"+f"(d[12]),"+f"(d[13]),"+f"(d[14]),"+f"(d[15]),"+f"(d[16]),"+f"(d[17]),"+f"(d[18]),"+f"(d[19]),"+f"(d[20]),"+f"(d[21]),"+f"(d[22]),"+f"(d[23]),"+f"(d[24]),"+f"(d[25]),"+f"(d[26]),"+f"(d[27]),"+f"(d[28]),"+f"(d[29]),"+f"(d[30]),"+f"(d[31])
    : "l"(da), "l"(db), "r"(sd), "n"(TB));
}
template<int TB> __device__ __forceinline__ void wgmma_ss_112(float* d, uint64_t da, uint64_t db, int sd) {
  asm volatile("{\n.reg .pred p;\nsetp.ne.b32 p, %58, 0;\n"
    "wgmma.mma_async.sync.aligned.m64n112k16.f32.bf16.bf16 {%0,%1,%2,%3,%4,%5,%6,%7,%8,%9,%10,%11,%12,%13,%14,%15,%16,%17,%18,%19,%20,%21,%22,%23,%24,%25,%26,%27,%28,%29,%30,%31,%32,%33,%34,%35,%36,%37,%38,%39,%40,%41,%42,%43,%44,%45,%46,%47,%48,%49,%50,%51,%52,%53,%54,%55}, %56, %57, p, 1, 1, 0, %59;\n}\n"
    : "+f"(d[0]),"+f"(d[1]),"+f"(d[2]),"+f"(d[3]),"+f"(d[4]),"+f"(d[5]),"+f"(d[6]),"+f"(d[7]),"+f"(d[8]),"+f"(d[9]),"+f"(d[10]),"+f"(d[11]),"+f"(d[12]),"+f"(d[13]),"+f"(d[14]),"+f"(d[15]),"+f"(d[16]),"+f"(d[17]),"+f"(d[18]),"+f"(d[19]),"+f"(d[20]),"+f"(d[21]),"+f"(d[22]),"+f"(d[23]),"+f"(d[24]),"+f"(d[25]),"+f"(d[26]),"+f"(d[27]),"+f"(d[28]),"+f"(d[29]),"+f"(d[30]),"+f"(d[31]),"+f"(d[32]),"+f"(d[33]),"+f"(d[34]),"+f"(d[35]),"+f"(d[36]),"+f"(d[37]),"+f"(d[38]),"+f"(d[39]),"+f"(d[40]),"+f"(d[41]),"+f"(d[42]),"+f"(d[43]),"+f"(d[44]),"+f"(d[45]),"+f"(d[46]),"+f"(d[47]),"+f"(d[48]),"+f"(d[49]),"+f"(d[50]),"+f"(d[51]),"+f"(d[52]),"+f"(d[53]),"+f"(d[54]),"+f"(d[55])
    : "l"(da), "l"(db), "r"(sd), "n"(TB));
}
template<int TB> __device__ __forceinline__ void wgmma_rs_112(float* d, uint32_t a0, uint32_t a1, uint32_t a2, uint32_t a3, uint64_t db, int sd) {
  asm volatile("{\n.reg .pred p;\nsetp.ne.b32 p, %61, 0;\n"
    "wgmma.mma_async.sync.aligned.m64n112k16.f32.bf16.bf16 {%0,%1,%2,%3,%4,%5,%6,%7,%8,%9,%10,%11,%12,%13,%14,%15,%16,%17,%18,%19,%20,%21,%22,%23,%24,%25,%26,%27,%28,%29,%30,%31,%32,%33,%34,%35,%36,%37,%38,%39,%40,%41,%42,%43,%44,%45,%46,%47,%48,%49,%50,%51,%52,%53,%54,%55}, {%56,%57,%58,%59}, %60, p, 1, 1, %62;\n}\n"
    : "+f"(d[0]),"+f"(d[1]),"+f"(d[2]),"+f"(d[3]),"+f"(d[4]),"+f"(d[5]),"+f"(d[6]),"+f"(d[7]),"+f"(d[8]),"+f"(d[9]),"+f"(d[10]),"+f"(d[11]),"+f"(d[12]),"+f"(d[13]),"+f"(d[14]),"+f"(d[15]),"+f"(d[16]),"+f"(d[17]),"+f"(d[18]),"+f"(d[19]),"+f"(d[20]),"+f"(d[21]),"+f"(d[22]),"+f"(d[23]),"+f"(d[24]),"+f"(d[25]),"+f"(d[26]),"+f"(d[27]),"+f"(d[28]),"+f"(d[29]),"+f"(d[30]),"+f"(d[31]),"+f"(d[32]),"+f"(d[33]),"+f"(d[34]),"+f"(d[35]),"+f"(d[36]),"+f"(d[37]),"+f"(d[38]),"+f"(d[39]),"+f"(d[40]),"+f"(d[41]),"+f"(d[42]),"+f"(d[43]),"+f"(d[44]),"+f"(d[45]),"+f"(d[46]),"+f"(d[47]),"+f"(d[48]),"+f"(d[49]),"+f"(d[50]),"+f"(d[51]),"+f"(d[52]),"+f"(d[53]),"+f"(d[54]),"+f"(d[55])
    : "r"(a0), "r"(a1), "r"(a2), "r"(a3), "l"(db), "r"(sd), "n"(TB));
}

constexpr int DM = 448;
constexpr int NCTA = 128;
#define MAPPING 1
#define GRID 132
#define PINGPONG 0
#define WIN 4
#define WIN_END 25
#define UNR_G2 21
#define UNR_B 7
#define UNR_C 7
constexpr int kG2 = UNR_G2, kB = UNR_B, kC = UNR_C;
#define MAP_S 4
constexpr int SPIN_LIMIT = 1 << 22;

constexpr uint32_t OFF_X = 0, OFF_Y = 114688, OFF_MISC = 229376, SMEM_BYTES = 232448;
constexpr uint32_t Y_VR = 0, Y_K = 28672, Y_KOWN = 57344, Y_VOWN = 71680, Y_Q = 86016;
constexpr uint32_t HALF = 57344;
constexpr uint32_t M_BAR = OFF_MISC;
constexpr uint32_t M_ST = OFF_MISC + 512;
constexpr uint32_t M_G = OFF_MISC + 2304;
constexpr uint32_t M_EPOCH = OFF_MISC + 3040;
enum { B_XFULL = 0, B_FULLK = 7, B_FULLV = 8, B_FULLQ, B_KRFULL, B_VRFULL, B_WOFULL, B_XCH, B_FULL = 16, B_MOD1 = 28, B_MOD2, B_WMFULL,
       B_EMPTY = 32, B_XFREE = B_EMPTY + 12, B_GEMV, B_PEER,
       B_PUB = 47,
       B_WMFREE = 56, B_HRDY, B_GFULL = B_HRDY + 3, B_DONE = 31 };
constexpr uint32_t X_STAT = 49152;

__device__ uint32_t g_ticket;
__device__ __align__(128) uint32_t g_mod[8 * 6 * DM];
__device__ __align__(128) uint32_t g_flag[144 * 96];
__device__ __align__(128) uint32_t g_kv[17 * 8 * 2 * 3584];
__device__ __align__(128) uint32_t g_ox[2 * 34 * 14336];
#define g_o g_ox
#define g_x1 (g_ox + 34 * 14336)
__device__ __align__(128) float2 g_st[34 * 8 * 64];
__device__ __align__(128) uint32_t g_h2[17 * 224 * 512];
#define PROFH(id)
#define PROFH1(id)
#define PROFC(id)

struct alignas(64) Params {
    CUtensorMap wm, xm, qkv, wo, ga, ua, gb, ub, gc, uc, dn;
    const bf16 *x, *c, *wqkv, *wmod, *wg, *wu, *wd, *wop;
    bf16* out;
    uint32_t zero;
};

__device__ __forceinline__ void mbar_init(uint32_t bar, int cnt) { asm volatile("mbarrier.init.shared::cta.b64 [%0], %1;" ::"r"(bar), "r"(cnt) : "memory"); }
__device__ __forceinline__ void mbar_expect_tx(uint32_t bar, uint32_t bytes) { asm volatile("mbarrier.arrive.expect_tx.shared::cta.b64 _, [%0], %1;" ::"r"(bar), "r"(bytes) : "memory"); }
__device__ __forceinline__ void mbar_arrive(uint32_t bar) { asm volatile("mbarrier.arrive.shared::cta.b64 _, [%0];" ::"r"(bar) : "memory"); }
__device__ __forceinline__ void mbar_wait(uint32_t bar, uint32_t parity) {
    uint32_t ok; int n = 0;
    do {
        asm volatile("{\n.reg .pred p;\nmbarrier.try_wait.parity.shared::cta.b64 p, [%1], %2;\nselp.u32 %0, 1, 0, p;\n}" : "=r"(ok) : "r"(bar), "r"(parity) : "memory");
        if (++n > SPIN_LIMIT) __trap();
    } while (!ok);
}
__device__ __forceinline__ void mbar_wait_c(uint32_t bar, uint32_t parity) {
    asm volatile("{\n.reg .pred p;\nWL:\nmbarrier.try_wait.parity.shared::cta.b64 p, [%0], %1;\n@!p bra WL;\n}" ::"r"(bar), "r"(parity) : "memory");
}
__device__ __forceinline__ void mbar_wait_cluster(uint32_t bar, uint32_t parity) {
    uint32_t ok; int n = 0;
    do {
        asm volatile("{\n.reg .pred p;\nmbarrier.try_wait.parity.acquire.cluster.shared::cta.b64 p, [%1], %2;\nselp.u32 %0, 1, 0, p;\n}" : "=r"(ok) : "r"(bar), "r"(parity) : "memory");
        if (++n > SPIN_LIMIT) __trap();
    } while (!ok);
}
__device__ __forceinline__ void warp_arrive(uint32_t bar) {
    __syncwarp();
    asm volatile("{\n.reg .pred p;\nelect.sync _|p, 0xffffffff;\n@p mbarrier.arrive.shared::cta.b64 _, [%0];\n}" ::"r"(bar) : "memory");
}
__device__ __forceinline__ int opaque(int v) { return __shfl_sync(~0u, v, 0); }
__device__ __forceinline__ int fresh_tid() { int v; asm volatile("mov.u32 %0, %%tid.x;" : "=r"(v)); return v; }
__device__ __forceinline__ void bar_sync(int id, int n) { asm volatile("bar.sync %0, %1;" ::"r"(id), "r"(n) : "memory"); }
__device__ __forceinline__ void bar_arrive(int id, int n) { asm volatile("bar.arrive %0, %1;" ::"r"(id), "r"(n) : "memory"); }
__device__ __forceinline__ void fence_async_smem() { asm volatile("fence.proxy.async.shared::cta;" ::: "memory"); }
__device__ __forceinline__ void fence_async_global() { asm volatile("fence.proxy.async.global;" ::: "memory"); }
__device__ __forceinline__ void fence_gpu() { asm volatile("fence.release.gpu;" ::: "memory"); }
__device__ __forceinline__ void tma3(uint32_t dst, const CUtensorMap* m, int c0, int c1, int c2, uint32_t bar) {
    asm volatile("cp.async.bulk.tensor.3d.shared::cluster.global.mbarrier::complete_tx::bytes [%0], [%1, {%3, %4, %5}], [%2];"
                 ::"r"(dst), "l"(m), "r"(bar), "r"(c0), "r"(c1), "r"(c2) : "memory");
}
__device__ __forceinline__ void bulk_load(uint32_t dst, const void* src, uint32_t bytes, uint32_t bar) {
    asm volatile("cp.async.bulk.shared::cluster.global.mbarrier::complete_tx::bytes [%0], [%1], %2, [%3];" ::"r"(dst), "l"(src), "r"(bytes), "r"(bar) : "memory");
}
__device__ __forceinline__ void expect_e(uint32_t bar, uint32_t bytes) {
    asm volatile("{\n.reg .pred p;\nelect.sync _|p, 0xffffffff;\n@p mbarrier.arrive.expect_tx.shared::cta.b64 _, [%0], %1;\n}" ::"r"(bar), "r"(bytes) : "memory");
}
__device__ __forceinline__ void tma3_e(uint32_t dst, const CUtensorMap* m, int c0, int c1, int c2, uint32_t bar) {
    asm volatile("{\n.reg .pred p;\nelect.sync _|p, 0xffffffff;\n@p cp.async.bulk.tensor.3d.shared::cluster.global.mbarrier::complete_tx::bytes [%0], [%1, {%3, %4, %5}], [%2];\n}"
                 ::"r"(dst), "l"(m), "r"(bar), "r"(c0), "r"(c1), "r"(c2) : "memory");
}
__device__ __forceinline__ void bulk_e(uint32_t dst, const void* src, uint32_t bytes, uint32_t bar) {
    asm volatile("{\n.reg .pred p;\nelect.sync _|p, 0xffffffff;\n@p cp.async.bulk.shared::cluster.global.mbarrier::complete_tx::bytes [%0], [%1], %2, [%3];\n}"
                 ::"r"(dst), "l"(src), "r"(bytes), "r"(bar) : "memory");
}
__device__ __forceinline__ void init_e(uint32_t bar, int cnt) {
    asm volatile("{\n.reg .pred p;\nelect.sync _|p, 0xffffffff;\n@p mbarrier.init.shared::cta.b64 [%0], %1;\n}" ::"r"(bar), "r"(cnt) : "memory");
}
__device__ __forceinline__ void l2_prefetch_e(const void* src, uint32_t bytes) {
    asm volatile("{\n.reg .pred p;\nelect.sync _|p, 0xffffffff;\n@p cp.async.bulk.prefetch.L2.global [%0], %1;\n}" ::"l"(src), "r"(bytes) : "memory");
}
__device__ __forceinline__ uint32_t ld_relaxed(const uint32_t* p) { uint32_t v; asm volatile("ld.relaxed.gpu.global.u32 %0, [%1];" : "=r"(v) : "l"(p) : "memory"); return v; }
__device__ __forceinline__ void st_relaxed(uint32_t* p, uint32_t v) { asm volatile("st.relaxed.gpu.global.u32 [%0], %1;" ::"l"(p), "r"(v) : "memory"); }
__device__ __forceinline__ uint4 ld_relaxed4(const uint4* p) { uint4 v; asm volatile("ld.relaxed.gpu.global.v4.u32 {%0,%1,%2,%3}, [%4];" : "=r"(v.x), "=r"(v.y), "=r"(v.z), "=r"(v.w) : "l"(p) : "memory"); return v; }
__device__ __forceinline__ void st_relaxed4(uint4* p, uint4 v) { asm volatile("st.relaxed.gpu.global.v4.u32 [%0], {%1,%2,%3,%4};" ::"l"(p), "r"(v.x), "r"(v.y), "r"(v.z), "r"(v.w) : "memory"); }
__device__ __forceinline__ uint4 ldg_nc4(const void* p) { uint4 v; asm volatile("ld.global.nc.L1::no_allocate.v4.u32 {%0,%1,%2,%3}, [%4];" : "=r"(v.x), "=r"(v.y), "=r"(v.z), "=r"(v.w) : "l"(p)); return v; }
__device__ __forceinline__ uint32_t ldg_nc(const void* p) { uint32_t v; asm volatile("ld.global.nc.u32 %0, [%1];" : "=r"(v) : "l"(p)); return v; }
__device__ __forceinline__ uint32_t ld_acquire(const uint32_t* p) { uint32_t v; asm volatile("ld.acquire.gpu.global.u32 %0, [%1];" : "=r"(v) : "l"(p) : "memory"); return v; }
__device__ __forceinline__ uint4 lds4(uint32_t a) { uint4 v; asm volatile("ld.shared.v4.u32 {%0,%1,%2,%3}, [%4];" : "=r"(v.x), "=r"(v.y), "=r"(v.z), "=r"(v.w) : "r"(a) : "memory"); return v; }
__device__ __forceinline__ float2 lds2f(uint32_t a) { float2 v; asm volatile("ld.shared.v2.f32 {%0,%1}, [%2];" : "=f"(v.x), "=f"(v.y) : "r"(a) : "memory"); return v; }
__device__ __forceinline__ uint32_t lds1(uint32_t a) { uint32_t v; asm volatile("ld.shared.u32 %0, [%1];" : "=r"(v) : "r"(a) : "memory"); return v; }
__device__ __forceinline__ void sts4(uint32_t a, uint4 v) { asm volatile("st.shared.v4.u32 [%0], {%1,%2,%3,%4};" ::"r"(a), "r"(v.x), "r"(v.y), "r"(v.z), "r"(v.w) : "memory"); }
__device__ __forceinline__ void sts2(uint32_t a, uint32_t x, uint32_t y) { asm volatile("st.shared.v2.u32 [%0], {%1,%2};" ::"r"(a), "r"(x), "r"(y) : "memory"); }
__device__ __forceinline__ void sts1(uint32_t a, uint32_t v) { asm volatile("st.shared.u32 [%0], %1;" ::"r"(a), "r"(v) : "memory"); }
__device__ __forceinline__ void stsm4(uint32_t a, uint32_t r0, uint32_t r1, uint32_t r2, uint32_t r3) {
    asm volatile("stmatrix.sync.aligned.m8n8.x4.shared.b16 [%0], {%1,%2,%3,%4};" ::"r"(a), "r"(r0), "r"(r1), "r"(r2), "r"(r3));
}
__device__ __forceinline__ uint32_t pack2(float lo, float hi) { uint32_t r; asm("cvt.rn.bf16x2.f32 %0, %1, %2;" : "=r"(r) : "f"(hi), "f"(lo)); return r; }
__device__ __forceinline__ uint32_t pack2_relu(float lo, float hi) { uint32_t r; asm("cvt.rn.relu.bf16x2.f32 %0, %1, %2;" : "=r"(r) : "f"(hi), "f"(lo)); return r; }
__device__ __forceinline__ uint32_t hfma2(uint32_t a, uint32_t b, uint32_t c) { uint32_t r; asm("fma.rn.bf16x2 %0, %1, %2, %3;" : "=r"(r) : "r"(a), "r"(b), "r"(c)); return r; }
__device__ __forceinline__ uint32_t hmul2(uint32_t a, uint32_t b) { uint32_t r; asm("mul.rn.bf16x2 %0, %1, %2;" : "=r"(r) : "r"(a), "r"(b)); return r; }
__device__ __forceinline__ float bf_lo(uint32_t v) { return __uint_as_float(v << 16); }
__device__ __forceinline__ float bf_hi(uint32_t v) { return __uint_as_float(v & 0xFFFF0000u); }
__device__ __forceinline__ float bf_round(float v) { return bf_lo(pack2(v, 0.f)); }
__device__ __forceinline__ float ex2(float x) { float r; asm("ex2.approx.ftz.f32 %0, %1;" : "=f"(r) : "f"(x)); return r; }
__device__ __forceinline__ void mma16816(float* d, uint32_t a0, uint32_t a1, uint32_t a2, uint32_t a3, uint32_t b0, uint32_t b1) {
    asm("mma.sync.aligned.m16n8k16.row.col.f32.bf16.bf16.f32 {%0,%1,%2,%3}, {%4,%5,%6,%7}, {%8,%9}, {%0,%1,%2,%3};"
        : "+f"(d[0]), "+f"(d[1]), "+f"(d[2]), "+f"(d[3]) : "r"(a0), "r"(a1), "r"(a2), "r"(a3), "r"(b0), "r"(b1));
}
__device__ __forceinline__ void mma16816_first(float* d, uint32_t a0, uint32_t a1, uint32_t a2, uint32_t a3, uint32_t b0, uint32_t b1) {
    asm volatile("mma.sync.aligned.m16n8k16.row.col.f32.bf16.bf16.f32 {%0,%1,%2,%3}, {%4,%5,%6,%7}, {%8,%9}, {%10,%10,%10,%10};"
        : "=f"(d[0]), "=f"(d[1]), "=f"(d[2]), "=f"(d[3]) : "r"(a0), "r"(a1), "r"(a2), "r"(a3), "r"(b0), "r"(b1), "f"(0.f));
}
__device__ __forceinline__ void mma16816_v(float* d, uint32_t a0, uint32_t a1, uint32_t a2, uint32_t a3, uint32_t b0, uint32_t b1) {
    asm volatile("mma.sync.aligned.m16n8k16.row.col.f32.bf16.bf16.f32 {%0,%1,%2,%3}, {%4,%5,%6,%7}, {%8,%9}, {%0,%1,%2,%3};"
        : "+f"(d[0]), "+f"(d[1]), "+f"(d[2]), "+f"(d[3]) : "r"(a0), "r"(a1), "r"(a2), "r"(a3), "r"(b0), "r"(b1));
}
__device__ __forceinline__ void mma1688(float* d, uint32_t a0, uint32_t a1, uint32_t b0) {
    asm("mma.sync.aligned.m16n8k8.row.col.f32.bf16.bf16.f32 {%0,%1,%2,%3}, {%4,%5}, {%6}, {%0,%1,%2,%3};"
        : "+f"(d[0]), "+f"(d[1]), "+f"(d[2]), "+f"(d[3]) : "r"(a0), "r"(a1), "r"(b0));
}
__device__ __forceinline__ void ldsm4(uint32_t a, uint32_t* r) {
    asm volatile("ldmatrix.sync.aligned.m8n8.x4.shared.b16 {%0,%1,%2,%3}, [%4];" : "=r"(r[0]), "=r"(r[1]), "=r"(r[2]), "=r"(r[3]) : "r"(a));
}
__device__ __forceinline__ void ldsm4t(uint32_t a, uint32_t* r) {
    asm volatile("ldmatrix.sync.aligned.m8n8.x4.trans.shared.b16 {%0,%1,%2,%3}, [%4];" : "=r"(r[0]), "=r"(r[1]), "=r"(r[2]), "=r"(r[3]) : "r"(a));
}
__device__ __forceinline__ float rcp(float x) { float r; asm("rcp.approx.ftz.f32 %0, %1;" : "=f"(r) : "f"(x)); return r; }
__device__ __forceinline__ uint2 ld_relaxed2(const void* p) { uint2 v; asm volatile("ld.relaxed.gpu.global.v2.u32 {%0,%1}, [%2];" : "=r"(v.x), "=r"(v.y) : "l"(p) : "memory"); return v; }
__device__ __forceinline__ void st_relaxed2(void* p, uint32_t x, uint32_t y) { asm volatile("st.relaxed.gpu.global.v2.u32 [%0], {%1,%2};" ::"l"(p), "r"(max(x, 1u)), "r"(max(y, 1u)) : "memory"); }
__device__ __forceinline__ constexpr uint64_t dconst(uint32_t lbo, uint32_t sbo, uint32_t swz) {
    return ((uint64_t)(lbo >> 4) << 16) | ((uint64_t)(sbo >> 4) << 32) | ((uint64_t)swz << 62);
}
__device__ __forceinline__ uint64_t mkdesc(uint32_t addr, uint64_t c) { return c | (uint64_t)((addr & 0x3FFFF) >> 4); }
#define WG_FENCE() asm volatile("wgmma.fence.sync.aligned;" ::: "memory")
#define WG_COMMIT() asm volatile("wgmma.commit_group.sync.aligned;" ::: "memory")
#define WG_WAIT(n) asm volatile("wgmma.wait_group.sync.aligned %0;" ::"n"(n) : "memory")
template <int N> __device__ __forceinline__ void reg_fence(float* d) {
#pragma unroll
    for (int i = 0; i < N; i++) asm volatile("" : "+f"(d[i])::"memory");
}
template <int N> __device__ __forceinline__ void reg_def(float* d) {
#pragma unroll
    for (int i = 0; i < N; i++) asm volatile("" : "=f"(d[i]));
}
template <int N> __device__ __forceinline__ void reg_def(uint32_t* d) {
#pragma unroll
    for (int i = 0; i < N; i++) asm volatile("" : "=r"(d[i]));
}
__device__ __forceinline__ bool is_unset(uint4 v) { return min(min(v.x, v.y), min(v.z, v.w)) == 0u; }
__device__ __forceinline__ uint4 nz4(uint32_t a, uint32_t b, uint32_t c, uint32_t d) { return make_uint4(max(a, 1u), max(b, 1u), max(c, 1u), max(d, 1u)); }
__device__ __forceinline__ void wait_flag(const uint32_t* p, uint32_t target) {
    int n = 0;
    while ((int)(ld_relaxed(p) - target) < 0) { if (++n > SPIN_LIMIT) __trap(); }
    asm volatile("fence.acquire.gpu;" ::: "memory");
}
__device__ __forceinline__ float silu_bf(uint32_t cbits) {
    const float c = __uint_as_float(cbits << 16);
    return bf_round(__fdividef(c, 1.f + fminf(ex2(-1.4426950408889634f * c), 1e30f)));
}
__device__ __forceinline__ void gemv_part(uint32_t wmbuf, int npanel, int wp, int lane) {
    const uint32_t wa = wmbuf + wp * 512 + (8 * (lane >> 4) + (lane & 7)) * 32 + ((lane >> 3) & 1) * 16;
    uint2 B[4];
#pragma unroll
    for (int i = 0; i < 4; i++) { const float2 v = lds2f(wmbuf + 28672 + (wp + 8 * i) * 32 + (lane & 3) * 8); B[i] = make_uint2(__float_as_uint(v.x), __float_as_uint(v.y)); }
#pragma unroll 1
    for (int pn = 0; pn < npanel; pn++) {
        float d[4] = {};
        uint32_t A[16];
#pragma unroll
        for (int i = 0; i < 4; i++) ldsm4t(wa + pn * 14336 + (i < 3 || wp < 4 ? i : 0) * 4096, A + 4 * i);
#pragma unroll
        for (int i = 0; i < 4; i++) mma16816(d, A[4 * i], A[4 * i + 1], A[4 * i + 2], A[4 * i + 3], B[i].x, B[i].y);
        if ((lane & 3) == 0) {
            sts1(wmbuf + 29696 + (wp * 32 + pn * 16 + (lane >> 2)) * 4, __float_as_uint(d[0]));
            sts1(wmbuf + 29696 + (wp * 32 + pn * 16 + 8 + (lane >> 2)) * 4, __float_as_uint(d[2]));
        }
    }
}
__device__ __forceinline__ int pass_f(int fs, int ps) { return 224 * fs + ((fs & 1) ? (ps == 0 ? 96 : ps == 1 ? 32 : 0) : (ps == 0 ? 0 : ps == 1 ? 128 : 192)); }
__device__ __forceinline__ constexpr uint32_t slot_off(int l) { return (l < 3 || l > 6 ? l : l == 6 ? 3 : l + 1) * 16384; }
__device__ __forceinline__ void ln_coeffs(float mean, float msq, uint32_t& r2, uint32_t& n2) {
    const float rs = bf_round(rsqrtf(fmaxf(msq - mean * mean, 0.f) + 1e-5f));
    r2 = pack2(rs, rs);
    n2 = pack2(-mean * rs, -mean * rs);
}

template <int sec> __device__ __forceinline__ void ring_loader(const Params& p, uint32_t sb_, int r_, int j_) {
    const uint32_t sb = opaque(sb_);
    const int r = opaque(r_), j = opaque(j_), nq = j >> 1, fs = 4 * (j & 1) + nq;
    const int fa = pass_f(fs, 0), fb = pass_f(fs, 1), fc = pass_f(fs, 2);
#define BAR(i) (sb + M_BAR + 8 * (i))
#define kh (j & 1)
            int sl = 0;
#pragma unroll 1
            for (int s = 0; s < 28; s++) {
                if (s >= 1 && s < 6) mbar_wait(BAR(B_FULL + s - 1), 0);
                const int ps = s < 14 ? 0 : s < 21 ? 1 : 2;
                const uint32_t half = ps < 2 ? 8192 : 4096;
                mbar_wait(BAR(B_EMPTY + sl), (s >= 7 && s < 14) || s >= 21);
                expect_e(BAR(B_FULL + sl), half);
                tma3_e(sb + slot_off(sl) + sec * half, &p.ga + 2 * ps + sec, 0, ps ? 64 * sl : 32 * s, ps == 0 ? fa >> 6 : ps == 1 ? fb >> 6 : fc >> 5, BAR(B_FULL + sl));
                sl = sl == 6 ? 0 : sl + 1;
            }
            if (!sec) PROFH(3);
#pragma unroll 1
            for (int e = 0; e < 4; e++) {
                const uint32_t dst = sb + slot_off(e) + sec * 8192, bar = BAR(B_FULL + e);
                const int f = (e < 2 ? fa + 64 * e : e == 2 ? fb : fc) + 32 * sec;
                mbar_wait(BAR(B_EMPTY + e), 0);
                expect_e(bar, e == 3 && sec ? 0 : 8192);
                if (!(e == 3 && sec)) { tma3_e(dst, &p.dn, 112 * nq + 48, f, 0, bar); tma3_e(dst + 4096, &p.dn, 112 * nq, f, 0, bar); }
            }
            sl = 4;
            int e = 4;
#pragma unroll 1
            for (int grp = 0; grp < 9; grp++) {
                const int ps = grp >= 6 ? 2 : grp >= 3 ? 1 : 0;
                int sidx = grp - 3 * ps;
                if (sec && sidx == 0) { mbar_wait(BAR(B_HRDY + ps), 0); fence_async_global(); }
                sidx += sidx >= nq;
                int f = pass_f(4 * kh + sidx, ps);
#pragma unroll 1
                for (int k = 4 >> ps; k > 0; k--, e++, f += 32) {
                    const uint32_t dst = sb + slot_off(sl), bar = BAR(B_FULL + sl);
                    mbar_wait(BAR(B_EMPTY + sl), e >= 12 && e < 24);
                    if (e < WIN_END && e >= WIN) mbar_wait(BAR(B_FULL + (sl >= WIN ? sl - WIN : sl + 12 - WIN)), e - WIN >= 12);
                    expect_e(bar, 8192);
                    if (!sec) { tma3_e(dst, &p.dn, 112 * nq + 48, f, 0, bar); tma3_e(dst + 4096, &p.dn, 112 * nq, f, 0, bar); }
                    else bulk_e(dst + 8192, g_h2 + (size_t)r * (224 * 512) + f * 64, 8192, bar);
                    sl = sl == 11 ? 0 : sl + 1;
                }
            }
            if (!sec) PROFH(4);
}

__global__ void __cluster_dims__(2, 1, 1) __launch_bounds__(384, 1) fused_block_kernel(const __grid_constant__ Params p) {
    extern __shared__ __align__(1024) unsigned char smem[];
    const uint32_t sb = (uint32_t)__cvta_generic_to_shared(smem);
    const int tid = threadIdx.x, lane = tid & 31, warp = __shfl_sync(~0u, tid >> 5, 0);
    const int m = blockIdx.x >> 1;
    int r, nq;
    {
        int g, i;
        if (m < MAP_S) { g = m < 4 ? 15 : 16; i = m & 3; }
        else if (m < MAP_S + 32) { g = (m - MAP_S) & 7; i = (m - MAP_S) >> 3; }
        else if (m < MAP_S + 60) { i = (m - MAP_S - 32) / 7; g = 8 + (m - MAP_S - 32) - 7 * i; }
        else { g = 16; i = m & 3; }
        r = g; nq = i;
    }
    const int j = opaque(2 * nq + (blockIdx.x & 1)), b = 8 * r + j, fs = 4 * kh + nq;
    const uint32_t sc = r == 16;
    if (lane == 0 && warp < 9 && warp != 6 && warp != 7) {
        const int i0 = warp == 8 ? 0 : 8 + 8 * warp, cnt = warp == 0 || warp == 8 ? 1 : warp < 3 ? 2 : 8;
#pragma unroll
        for (int k = 0; k < 8; k++) if (i0 + k != B_WMFULL) mbar_init(BAR(i0 + k), cnt);
        asm volatile("fence.mbarrier_init.release.cluster;" ::: "memory");
        fence_async_smem();
    }

    if (warp < 8) {
        const int w = warp >> 2, wi = warp & 3;
#define COORDS const int t = fresh_tid() & 127, lane = t & 31, q = lane & 3, lr = lane >> 2, ra = 64 * w + 16 * wi + lr; \
        const uint32_t lx = (lane >> 4) ^ (lane & 7), mrow = (64 * w + 16 * wi + ((lane >> 3) & 1) * 8 + (lane & 7)) * 128; \
        (void)q; (void)lr; (void)ra; (void)lx; (void)mrow;
        const int sid = 2 * (j & 3) + w;
#define RUN(k) (!sc || sid == (k))
#define WAIT(i, par) mbar_wait_c(BAR(i), (par) | sc)
        constexpr uint64_t DB128 = dconst(4096, 1024, 1);
        bar_arrive(9, 384);
        bar_sync(0, 384);
        asm volatile("barrier.cluster.arrive.relaxed.aligned;" ::: "memory");
        asm volatile("setmaxnreg.inc.sync.aligned.u32 224;");
        PROFC(0);
        uint32_t xr[16];
        {
            COORDS
            uint32_t h[112];
            if (RUN(0)) {
                float ds[4] = {}, da[2][4] = {}, db[2][4] = {};
                const uint32_t ONE2 = 0x3F803F80u;
                if (kh == 0) { WAIT(B_WMFULL, 0); gemv_part(sb + OFF_Y + HALF, 1, warp, lane); warp_arrive(BAR(B_GEMV)); }
#pragma unroll
                for (int kb = 0; kb < 7; kb++) {
                    WAIT(B_XFULL + kb, 0);
#pragma unroll
                    for (int k4 = 0; k4 < 4; k4++) ldsm4(sb + OFF_X + mrow + kb * 16384 + (((2 * k4) ^ lx) << 4), h + 16 * kb + 4 * k4);
#pragma unroll
                    for (int k4 = 0; k4 < 4; k4++) {
                        const uint32_t* f = h + 16 * kb + 4 * k4;
                        mma16816(ds, f[0], f[1], f[2], f[3], ONE2, ONE2);
                        mma1688(da[0], f[0], f[1], f[0]); mma1688(db[0], f[0], f[1], f[1]);
                        mma1688(da[1], f[2], f[3], f[2]); mma1688(db[1], f[2], f[3], f[3]);
                    }
                }
#pragma unroll
                for (int i = 0; i < 4; i++) {
                    const int ch = 7 * j + 2 * i + (lane >> 4);
                    ldsm4(sb + OFF_X + mrow + (ch >> 3) * 16384 + (((ch ^ lane) & 7) << 4), xr + 4 * i);
                }
                warp_arrive(BAR(B_XFREE));
                float qa = (lr & 1) ? da[0][1] + da[1][1] : da[0][0] + da[1][0];
                float qb = (lr & 1) ? db[0][3] + db[1][3] : db[0][2] + db[1][2];
                const int src = (lane & ~3) | (lr >> 1);
                qa = __shfl_sync(~0u, qa, src);
                qb = __shfl_sync(~0u, qb, src);
                uint32_t ra2, na2, rb2, nb2;
                ln_coeffs(ds[0] * (1.f / DM), qa * (1.f / DM), ra2, na2);
                ln_coeffs(ds[2] * (1.f / DM), qb * (1.f / DM), rb2, nb2);
#pragma unroll
                for (int i = 0; i < 112; i += 2) { h[i] = hfma2(h[i], ra2, na2); h[i + 1] = hfma2(h[i + 1], rb2, nb2); }
                if (kh == 1) { WAIT(B_WMFULL, 0); gemv_part(sb + OFF_Y + HALF, 2, warp, lane); warp_arrive(BAR(B_GEMV)); }
            } else { reg_def<112>(h); reg_def<16>(xr); }
            PROFC(1);
            if (RUN(1)) {
                float ak[28], av[28], aq[28];
                uint32_t kp[14], vp[14];
                const uint64_t bk0 = mkdesc(sb + OFF_Y, DB128) + kh, bv0 = mkdesc(sb + OFF_Y + HALF, DB128) + kh, bq0 = mkdesc(sb + OFF_X, DB128) + kh;
                uint32_t* kvg = g_kv + (size_t)(b * 2) * 3584 + (8 * w + 2 * wi) * 224 + lane;
                WAIT(B_FULLK, 0);
                WAIT(B_MOD1, 0);
                PROFC(2);
                reg_def<28>(ak);
#pragma unroll
                for (int g4 = 0; g4 < 4; g4++) {
#pragma unroll
                    for (int ks = 7 * g4; ks < 7 * g4 + 7; ks++) {
                        const uint4 st = *(const uint4*)(smem + M_ST + ks * 64 + q * 16);
                        h[4 * ks] = hfma2(h[4 * ks], st.x, st.y); h[4 * ks + 1] = hfma2(h[4 * ks + 1], st.x, st.y);
                        h[4 * ks + 2] = hfma2(h[4 * ks + 2], st.z, st.w); h[4 * ks + 3] = hfma2(h[4 * ks + 3], st.z, st.w);
                    }
                    WG_FENCE();
#pragma unroll
                    for (int ks = 7 * g4; ks < 7 * g4 + 7; ks++) wgmma_rs_56<1>(ak, h[4 * ks], h[4 * ks + 1], h[4 * ks + 2], h[4 * ks + 3], bk0 + ks * 128, ks != 0);
                }
                WG_COMMIT();
                PROFC(3);
                WAIT(B_FULLV, 0);
                reg_def<28>(av);
                WG_FENCE();
#pragma unroll
                for (int ks = 0; ks < 8; ks++) wgmma_rs_56<1>(av, h[4 * ks], h[4 * ks + 1], h[4 * ks + 2], h[4 * ks + 3], bv0 + ks * 128, ks != 0);
                WG_COMMIT();
                WG_WAIT(1);
                reg_fence<28>(ak);
#pragma unroll
                for (int g = 0; g < 7; g++) {
                    kp[2 * g] = pack2(ak[4 * g], ak[4 * g + 1]); kp[2 * g + 1] = pack2(ak[4 * g + 2], ak[4 * g + 3]);
                    kvg[g * 32] = kp[2 * g]; kvg[224 + g * 32] = kp[2 * g + 1];
                }
                warp_arrive(BAR(B_PUB));
                PROFC(4);
                WG_FENCE();
#pragma unroll
                for (int ks = 8; ks < 28; ks++) wgmma_rs_56<1>(av, h[4 * ks], h[4 * ks + 1], h[4 * ks + 2], h[4 * ks + 3], bv0 + ks * 128, 1);
                WG_COMMIT();
                WAIT(B_FULLQ, 0);
                reg_def<28>(aq);
                WG_FENCE();
#pragma unroll
                for (int ks = 0; ks < 8; ks++) wgmma_rs_56<1>(aq, h[4 * ks], h[4 * ks + 1], h[4 * ks + 2], h[4 * ks + 3], bq0 + ks * 128, ks != 0);
                WG_COMMIT();
                WG_WAIT(1);
                reg_fence<28>(av);
#pragma unroll
                for (int g = 0; g < 7; g++) {
                    vp[2 * g] = pack2(av[4 * g], av[4 * g + 1]); vp[2 * g + 1] = pack2(av[4 * g + 2], av[4 * g + 3]);
                    kvg[3584 + g * 32] = vp[2 * g]; kvg[3584 + 224 + g * 32] = vp[2 * g + 1];
                }
                warp_arrive(BAR(B_PUB + 1));
                PROFC(5);
                WG_FENCE();
#pragma unroll
                for (int ks = 8; ks < 28; ks++) wgmma_rs_56<1>(aq, h[4 * ks], h[4 * ks + 1], h[4 * ks + 2], h[4 * ks + 3], bq0 + ks * 128, 1);
                WG_COMMIT();
                WAIT(B_PUB + 1, 0);
                const uint32_t ko = sb + OFF_Y + Y_KOWN + (8 * w + 2 * wi) * 896 + lane * 4;
                const uint32_t qo = sb + OFF_Y + Y_Q + (8 * w + 2 * wi) * 1024 + lane * 4;
#pragma unroll
                for (int g = 0; g < 7; g++) {
                    sts1(ko + g * 128, kp[2 * g]); sts1(ko + 896 + g * 128, kp[2 * g + 1]);
                    sts1(ko + (Y_VOWN - Y_KOWN) + g * 128, vp[2 * g]); sts1(ko + (Y_VOWN - Y_KOWN) + 896 + g * 128, vp[2 * g + 1]);
                }
                WG_WAIT(0);
                reg_fence<28>(aq);
                __syncwarp();
                if (lane < 3 && w == 1) mbar_arrive(BAR(B_EMPTY + lane));
#pragma unroll
                for (int g = 0; g < 7; g++) {
                    const uint32_t q0 = pack2(aq[4 * g], aq[4 * g + 1]), q1 = pack2(aq[4 * g + 2], aq[4 * g + 3]);
                    if (g == 3) {
                        sts1(qo + 3 * 128, q < 2 ? q0 : 0u); sts1(qo + 1024 + 3 * 128, q < 2 ? q1 : 0u);
                        sts1(qo + 4 * 128, q < 2 ? 0u : q0); sts1(qo + 1024 + 4 * 128, q < 2 ? 0u : q1);
                    } else {
                        const int ch = g < 3 ? g : g + 1;
                        sts1(qo + ch * 128, q0); sts1(qo + 1024 + ch * 128, q1);
                    }
                }
                if (!sc) bar_sync(3, 256);
            }
        }
        PROFC(6);
        WAIT(B_KRFULL, 0);
        PROFC(7);
        if (RUN(2)) {
#pragma unroll 1
            for (int hf = sc; hf < 2; hf++) {
                COORDS
                float s[136];
                float na = 0.f, nb = 0.f;
                const float CS = 0.18898223650461361f * 1.4426950408889634f;
                const int kg0 = 8 * hf + 2 * wi;
                const int pmin = 16 - 8 * r - 4 * hf - wi;
                const float NEG = __int_as_float(0xFF800000);
                {
                    uint32_t F[8];
                    const uint32_t qa = sb + OFF_Y + Y_Q + (kg0 + ((lane >> 3) & 1)) * 1024 + (4 * w + (lane >> 4)) * 128 + (lane & 7) * 16;
                    ldsm4(qa, F); ldsm4(qa + 256, F + 4);
                    uint32_t ka = sb + OFF_Y + Y_K + kg0 * 896 + (3 * w + (lane >> 3)) * 128 + (lane & 7) * 16;
#pragma unroll
                    for (int g = 0; g < 34; g++) {
                        uint32_t B[4];
                        if (g >= 12 && g % 4 == 0) ka += __float_as_uint(s[4 * (g - 12)]) & p.zero;
                        ldsm4(ka + g * 896, B);
                        mma16816_first(s + 4 * g, F[0], F[1], F[2], F[3], B[0], B[1]);
                        mma16816_v(s + 4 * g, F[4], F[5], F[6], F[7], B[2], B[3]);
                    }
                    const bool c0 = 2 * q > lr, c1 = 2 * q + 1 > lr;
                    if (!c0) { s[0] = NEG; s[6] = NEG; }
                    if (!c1) { s[1] = NEG; s[7] = NEG; }
                    s[2] = NEG; s[3] = NEG;
                    if (c0) { s[128] = NEG; s[134] = NEG; }
                    if (c1) { s[129] = NEG; s[135] = NEG; }
                    s[132] = NEG; s[133] = NEG;
                    float ma = NEG, mb = NEG;
#pragma unroll
                    for (int pp = 0; pp < 17; pp++) {
                        const float* e = s + 8 * pp;
                        const float bias = pp < pmin ? NEG : 0.f;
                        ma = fmaxf(ma, fmaxf(fmaxf(e[0], e[1]), fmaxf(e[4], e[5])) + bias);
                        mb = fmaxf(mb, fmaxf(fmaxf(e[2], e[3]), fmaxf(e[6], e[7])) + bias);
                    }
                    ma = fmaxf(ma, __shfl_xor_sync(~0u, ma, 1)); mb = fmaxf(mb, __shfl_xor_sync(~0u, mb, 1));
                    ma = fmaxf(ma, __shfl_xor_sync(~0u, ma, 2)); mb = fmaxf(mb, __shfl_xor_sync(~0u, mb, 2));
                    na = -ma * CS; nb = -mb * CS;
                }
                PROFC(8 + 3 * hf);
                {
                    WAIT(B_VRFULL, 0);
                    float o[16] = {}, rs[4] = {};
                    uint32_t pk[2];
                    const uint32_t va = sb + OFF_Y + Y_VR + (kg0 + ((lane >> 3) & 1)) * 896 + (3 * w + (lane >> 4)) * 128 + (lane & 7) * 16;
#pragma unroll
                    for (int pp = 0; pp < 17; pp++) {
                        uint32_t B[8];
                        const uint32_t v = va + pp * 1792 + (pp == 16 || (pp >= 9 && kg0 + 2 * pp >= 32) ? Y_VOWN - 32 * 896 : 0);
                        ldsm4t(v, B); ldsm4t(v + 256, B + 4);
                        float e[8];
                        const float bias = __uint_as_float((pp < pmin ? 0xFF800000u : 0u) | ((pp < 2 ? B[0] : pk[pp & 1]) & p.zero));
#pragma unroll
                        for (int i = 0; i < 8; i++) e[i] = ex2(fmaf(s[8 * pp + i], CS, ((i & 2) ? nb : na) + bias));
                        const uint32_t p0 = pack2(e[0], e[1]), p1 = pack2(e[2], e[3]), p2 = pack2(e[4], e[5]), p3 = pack2(e[6], e[7]);
                        pk[pp & 1] = p3;
                        mma16816(rs, p0, p1, p2, p3, 0x3F803F80u, 0x3F803F80u);
#pragma unroll
                        for (int g = 0; g < 4; g++) mma16816(o + 4 * g, p0, p1, p2, p3, B[2 * g], B[2 * g + 1]);
                    }
                    PROFC(9 + 3 * hf);
                    const float ia = rcp(rs[0]), ib = rcp(rs[2]);
                    uint32_t* og = g_o + (size_t)(2 * r + hf) * 14336 + (7 * j + 3 * w) * 256 + wi * 64 + lane;
#pragma unroll
                    for (int g = 0; g < 4; g++) {
                        if ((g == 3 - 3 * w) ? ((q >> 1) == w) : true) {
                            og[g * 256] = pack2(o[4 * g] * ia, o[4 * g + 1] * ia);
                            og[g * 256 + 32] = pack2(o[4 * g + 2] * ib, o[4 * g + 3] * ib);
                        }
                    }
                    warp_arrive(BAR(B_PUB + 2 + hf));
                    PROFC(10 + 3 * hf);
                }
            }
        }
        uint32_t x1p[14];
        COORDS
        constexpr uint64_t DT = dconst(1024, 128, 0);
        if (RUN(4)) {
            float ac[28];
            const uint64_t ad = mkdesc(sb + (w ? OFF_Y + HALF : OFF_X), DT), bd = mkdesc(sb + OFF_X + HALF, DB128) + kh;
            WAIT(B_WOFULL, 0);
            WAIT(B_MOD2, 0);
            WAIT(B_GFULL + w, 0);
            PROFC(28);
            reg_def<28>(ac);
#pragma unroll 1
            for (int u = 0; u < 4; u++) {
                WG_FENCE();
#pragma unroll
                for (int i = 0; i < 7; i++) wgmma_ss_56<1>(ac, ad + (7 * u + i) * 128, bd + (7 * u + i) * 128, (u | i) != 0);
            }
            WG_COMMIT();
            WG_WAIT(0);
            reg_fence<28>(ac);
            PROFC(14);
            __syncwarp();
            if (lane < 3) mbar_arrive(BAR(B_EMPTY + 3 + lane));
            if (lane < 3 && w == 0) mbar_arrive(BAR(B_EMPTY + lane));
            float s1a = 0.f, s2a = 0.f, s1b = 0.f, s2b = 0.f;
            uint32_t* xo = g_x1 + (size_t)(2 * r + w) * 14336 + 7 * j * 256 + wi * 64 + lane;
#pragma unroll
            for (int g = 0; g < 7; g++) {
                const float2 ga = *(const float2*)(smem + M_G + (8 * g + 2 * q) * 4);
                x1p[2 * g] = pack2(fmaf(ga.x, ac[4 * g], bf_lo(xr[2 * g])), fmaf(ga.y, ac[4 * g + 1], bf_hi(xr[2 * g])));
                x1p[2 * g + 1] = pack2(fmaf(ga.x, ac[4 * g + 2], bf_lo(xr[2 * g + 1])), fmaf(ga.y, ac[4 * g + 3], bf_hi(xr[2 * g + 1])));
                xo[g * 256] = x1p[2 * g]; xo[g * 256 + 32] = x1p[2 * g + 1];
                const float u0 = bf_lo(x1p[2 * g]), u1 = bf_hi(x1p[2 * g]), u2 = bf_lo(x1p[2 * g + 1]), u3 = bf_hi(x1p[2 * g + 1]);
                s1a += u0 + u1; s2a += u0 * u0 + u1 * u1; s1b += u2 + u3; s2b += u2 * u2 + u3 * u3;
            }
            float ka = (q & 1) ? s2a : s1a, kb2 = (q & 1) ? s2b : s1b;
            ka += __shfl_xor_sync(~0u, (q & 1) ? s1a : s2a, 1); kb2 += __shfl_xor_sync(~0u, (q & 1) ? s1b : s2b, 1);
            const float kk = ((q & 2) ? kb2 : ka) + __shfl_xor_sync(~0u, (q & 2) ? ka : kb2, 2);
            ((float*)g_st)[(((2 * r + w) * 8 + j) * 64 + 16 * wi + lr + 4 * (q & 2)) * 2 + (q & 1)] = kk;
            __syncwarp();
            if (lane < 2) mbar_arrive(BAR(B_PUB + 4 + w));
        } else reg_def<14>(x1p);
        PROFC(15);
        uint32_t h2a[32], h2b[24];
        if (RUN(6)) {
            const int fa = pass_f(fs, 0), fb = pass_f(fs, 1), fc = pass_f(fs, 2);
            uint32_t* h2g = g_h2 + (size_t)r * (224 * 512) + (8 * w + 2 * wi) * 32 + lane;
            const uint64_t a0 = mkdesc(sb + OFF_Y + w * HALF, DT);
            {
                WAIT(B_GFULL + 2 + w, 0);
                PROFC(16);
                float2 sa = make_float2(0.f, 0.f), sbb = sa;
#pragma unroll
                for (int jj = 0; jj < 8; jj++) {
                    const float2 u = lds2f(sb + OFF_X + X_STAT + w * 4096 + (jj * 64 + 16 * wi + lr) * 8), v = lds2f(sb + OFF_X + X_STAT + w * 4096 + (jj * 64 + 16 * wi + lr + 8) * 8);
                    sa.x += u.x; sa.y += u.y; sbb.x += v.x; sbb.y += v.y;
                }
                warp_arrive(BAR(B_EMPTY + 6));
                uint32_t ra2, na2, rb2, nb2;
                ln_coeffs(sa.x * (1.f / DM), sa.y * (1.f / DM), ra2, na2);
                ln_coeffs(sbb.x * (1.f / DM), sbb.y * (1.f / DM), rb2, nb2);
                const uint32_t ha = sb + OFF_Y + w * HALF + (lane >> 4) * 1024 + (2 * wi + ((lane >> 3) & 1)) * 128 + (lane & 7) * 16;
                const uint32_t sta = sb + M_ST + q * 16;
                auto prep = [&](int s, uint32_t* f) {
                    uint32_t x[8];
                    ldsm4(ha + s * 4096, x); ldsm4(ha + s * 4096 + 2048, x + 4);
                    const uint4 st[2] = {lds4(sta + s * 128), lds4(sta + s * 128 + 64)};
#pragma unroll
                    for (int i = 0; i < 2; i++) {
                        f[4 * i] = hfma2(hfma2(x[4 * i], ra2, na2), st[i].x, st[i].y); f[4 * i + 1] = hfma2(hfma2(x[4 * i + 1], rb2, nb2), st[i].x, st[i].y);
                        f[4 * i + 2] = hfma2(hfma2(x[4 * i + 2], ra2, na2), st[i].z, st[i].w); f[4 * i + 3] = hfma2(hfma2(x[4 * i + 3], rb2, nb2), st[i].z, st[i].w);
                    }
                    stsm4(ha + s * 4096, f[0], f[1], f[2], f[3]); stsm4(ha + s * 4096 + 2048, f[4], f[5], f[6], f[7]);
                };
                float ac[128];
                uint32_t fr[3][8];
                const uint64_t bx = mkdesc(sb, DB128);
                reg_def<128>(ac);
                prep(0, fr[0]);
                PROFC(17);
#pragma unroll
                for (int s = 0; s < 14; s++) {
                    const uint32_t* f = fr[s % 3];
                    const uint64_t bd = bx + (slot_off(s % 7) >> 4);
                    WAIT(B_FULL + s % 7, s >= 7);
                    WG_FENCE();
                    wgmma_rs_256<1>(ac, f[0], f[1], f[2], f[3], bd, s != 0);
                    wgmma_rs_256<1>(ac, f[4], f[5], f[6], f[7], bd + 128, 1);
                    WG_COMMIT();
                    if (s < 13) prep(s + 1, fr[(s + 1) % 3]);
                    if (s > 0) { WG_WAIT(1); warp_arrive(BAR(B_EMPTY + (s - 1) % 7)); }
                }
                PROFC(18);
                fence_async_smem();
                WG_WAIT(0);
                reg_fence<128>(ac);
                warp_arrive(BAR(B_EMPTY + 6));
#pragma unroll
                for (int g = 0; g < 16; g++) {
                    h2a[2 * g] = hmul2(pack2_relu(ac[4 * g], ac[4 * g + 1]), pack2(ac[64 + 4 * g], ac[64 + 4 * g + 1]));
                    h2a[2 * g + 1] = hmul2(pack2_relu(ac[4 * g + 2], ac[4 * g + 3]), pack2(ac[64 + 4 * g + 2], ac[64 + 4 * g + 3]));
                    h2g[(fa / 8 + g) * 512] = h2a[2 * g]; h2g[(fa / 8 + g) * 512 + 32] = h2a[2 * g + 1];
                }
                warp_arrive(BAR(B_PUB + 6));
                bar_sync(1 + w, 128);
            }
            PROFC(19);
            {
                float ac[64];
                reg_def<64>(ac);
                const uint64_t bx = mkdesc(sb, dconst(8192, 1024, 1));
#pragma unroll kB
                for (int s = 0; s < 7; s++) {
                    WAIT(B_FULL + s, 0);
                    const uint64_t ad = a0 + s * 512, bd = bx + (slot_off(s) >> 4);
                    WG_FENCE();
#pragma unroll
                    for (int k = 0; k < 4; k++) wgmma_ss_128<1>(ac, ad + k * 128, bd + k * 128, (s | k) != 0);
                    WG_COMMIT();
                    if (s > 0) { WG_WAIT(1); warp_arrive(BAR(B_EMPTY + s - 1)); }
                }
                WG_WAIT(0);
                reg_fence<64>(ac);
                warp_arrive(BAR(B_EMPTY + 6));
#pragma unroll
                for (int g = 0; g < 8; g++) {
                    h2b[2 * g] = hmul2(pack2_relu(ac[4 * g], ac[4 * g + 1]), pack2(ac[32 + 4 * g], ac[32 + 4 * g + 1]));
                    h2b[2 * g + 1] = hmul2(pack2_relu(ac[4 * g + 2], ac[4 * g + 3]), pack2(ac[32 + 4 * g + 2], ac[32 + 4 * g + 3]));
                    h2g[(fb / 8 + g) * 512] = h2b[2 * g]; h2g[(fb / 8 + g) * 512 + 32] = h2b[2 * g + 1];
                }
                warp_arrive(BAR(B_PUB + 7));
            }
            PROFC(27);
            {
                float ac[32];
                reg_def<32>(ac);
                const uint64_t bx = mkdesc(sb, dconst(4096, 512, 2));
#pragma unroll kC
                for (int s = 0; s < 7; s++) {
                    WAIT(B_FULL + s, 1);
                    const uint64_t ad = a0 + p.zero + s * 512, bd = bx + (slot_off(s) >> 4);
                    WG_FENCE();
#pragma unroll
                    for (int k = 0; k < 4; k++) wgmma_ss_64<1>(ac, ad + k * 128, bd + k * 64, (s | k) != 0);
                    WG_COMMIT();
                    if (s > 0) { WG_WAIT(1); warp_arrive(BAR(B_EMPTY + s - 1)); }
                }
                WG_WAIT(0);
                reg_fence<32>(ac);
                __syncwarp();
                if (lane < 6) mbar_arrive(BAR(B_EMPTY + 6 + lane));
                PROFC(20);
#pragma unroll
                for (int g = 0; g < 4; g++) {
                    h2b[16 + 2 * g] = hmul2(pack2_relu(ac[4 * g], ac[4 * g + 1]), pack2(ac[16 + 4 * g], ac[16 + 4 * g + 1]));
                    h2b[16 + 2 * g + 1] = hmul2(pack2_relu(ac[4 * g + 2], ac[4 * g + 3]), pack2(ac[16 + 4 * g + 2], ac[16 + 4 * g + 3]));
                    h2g[(fc / 8 + g) * 512] = h2b[16 + 2 * g]; h2g[(fc / 8 + g) * 512 + 32] = h2b[16 + 2 * g + 1];
                }
                warp_arrive(BAR(B_PUB + 8));
                asm volatile("barrier.cluster.wait.aligned;" ::: "memory");
                if (lane == 0 && !sc) {
                    uint32_t rb;
                    asm volatile("mapa.shared::cluster.u32 %0, %1, %2;" : "=r"(rb) : "r"(BAR(B_PEER)), "r"(kh ^ 1));
                    asm volatile("mbarrier.arrive.relaxed.cluster.shared::cluster.b64 _, [%0];" ::"r"(rb) : "memory");
                }
            }
        } else { reg_def<32>(h2a); reg_def<24>(h2b); }
        PROFC(21);
        if (RUN(7)) {
            float ac[56];
            reg_def<56>(ac);
            constexpr uint64_t DAN = dconst(2048, 128, 0);
            const uint64_t bx = mkdesc(sb, DB128);
#pragma unroll
            for (int e = 0; e < 4; e++) {
                WAIT(B_FULL + e, 0);
                const uint64_t bd = bx + (slot_off(e) >> 4);
                const uint32_t* hh = e < 2 ? h2a + 16 * e : h2b + 16 * (e - 2);
                WG_FENCE();
#pragma unroll
                for (int k = 0; k < (e < 3 ? 4 : 2); k++) wgmma_rs_112<1>(ac, hh[4 * k], hh[4 * k + 1], hh[4 * k + 2], hh[4 * k + 3], bd + (k >> 1) * 512 + (k & 1) * 128, (e | k) != 0);
                WG_COMMIT();
                if (e > 0) { WG_WAIT(1); warp_arrive(BAR(B_EMPTY + e - 1)); }
            }
            PROFC(22);
            const uint64_t ax = mkdesc(sb + 8192 + w * 1024, DAN);
#pragma unroll kG2
            for (int e = 4; e < 25; e++) {
                WAIT(B_FULL + e % 12, e >= 12 && e < 24);
                if (e == 16) PROFC(23);
                const uint64_t z = (e / 12) * p.zero;
                const uint64_t ad = ax + z + (slot_off(e % 12) >> 4), bd = bx + z + (slot_off(e % 12) >> 4);
                WG_FENCE();
                wgmma_ss_112<1>(ac, ad, bd, 1);
                wgmma_ss_112<1>(ac, ad + 256, bd + 128, 1);
                WG_COMMIT();
                if (e < 14) { WG_WAIT(1); warp_arrive(BAR(B_EMPTY + (e - 1) % 12)); }
            }
            mbar_wait_cluster(BAR(B_PEER), sc);
            WG_WAIT(0);
            reg_fence<56>(ac);
            PROFC(24);
            uint32_t rdst, rbar;
            asm volatile("mapa.shared::cluster.u32 %0, %1, %2;" : "=r"(rdst) : "r"(sb + OFF_Y + (5 + w) * 16384 + t * 16), "r"(kh ^ 1 ^ sc));
            asm volatile("mapa.shared::cluster.u32 %0, %1, %2;" : "=r"(rbar) : "r"(BAR(B_XCH + w)), "r"(kh ^ 1 ^ sc));
#define ACG(g, i) ac[4 * (((g) + 8) % 14) + (i)]
#pragma unroll
            for (int g = 0; g < 7; g++) {
                const float v0 = kh ? ACG(g, 0) : ACG(g + 7, 0), v1 = kh ? ACG(g, 1) : ACG(g + 7, 1);
                const float v2 = kh ? ACG(g, 2) : ACG(g + 7, 2), v3 = kh ? ACG(g, 3) : ACG(g + 7, 3);
                if (!sc) asm volatile("st.async.shared::cluster.mbarrier::complete_tx::bytes.v4.f32 [%0], {%1,%2,%3,%4}, [%5];"
                             ::"r"(rdst + g * 2048), "f"(v0), "f"(v1), "f"(v2), "f"(v3), "r"(rbar) : "memory");
            }
            mbar_wait_cluster(BAR(B_XCH + w), sc);
            PROFC(25);
            bf16* og = (sc ? (bf16*)(g_h2 + 16 * 224 * 512) : p.out + (size_t)128 * r * DM) + (size_t)ra * DM + 56 * j + 2 * q;
#pragma unroll
            for (int g = 0; g < 7; g++) {
                const uint4 rv = *(const uint4*)(smem + OFF_Y + (5 + w) * 16384 + t * 16 + g * 2048);
                const float2 gb = *(const float2*)(smem + M_G + 224 + (8 * g + 2 * q) * 4);
                const float v0 = (kh ? ACG(g + 7, 0) : ACG(g, 0)) + __uint_as_float(rv.x), v1 = (kh ? ACG(g + 7, 1) : ACG(g, 1)) + __uint_as_float(rv.y);
                const float v2 = (kh ? ACG(g + 7, 2) : ACG(g, 2)) + __uint_as_float(rv.z), v3 = (kh ? ACG(g + 7, 3) : ACG(g, 3)) + __uint_as_float(rv.w);
                *(uint32_t*)(og + 8 * g) = pack2(fmaf(gb.x, v0, bf_lo(x1p[2 * g])), fmaf(gb.y, v1, bf_hi(x1p[2 * g])));
                *(uint32_t*)(og + 8 * DM + 8 * g) = pack2(fmaf(gb.x, v2, bf_lo(x1p[2 * g + 1])), fmaf(gb.y, v3, bf_hi(x1p[2 * g + 1])));
            }
        }
        PROFC(26);
        bar_sync(1 + w, 128);
        if (wi == 0) warp_arrive(BAR(B_DONE));
    } else {
        const int lane = fresh_tid() & 31;
        const bool early = kh == 0, gemv = r < 14;
        const int mcol = early ? 16 * (4 * r + nq) : 2 * DM + 32 * (4 * r + nq);
        const uint32_t wmbuf = sb + OFF_Y + HALF;
        asm volatile("setmaxnreg.dec.sync.aligned.u32 56;");
        if (warp == 9) {
#pragma unroll
            for (int i = 56; i < 64; i++) init_e(BAR(i), 1);
            fence_async_smem();
        }
        if (warp == 8) { init_e(BAR(B_WMFULL), 2); fence_async_smem(); }
        bar_arrive(0, 384);
        asm volatile("barrier.cluster.arrive.relaxed.aligned;" ::: "memory");
        uint32_t target = 0;
        if (warp == 8) {
            if (!sc) {
                expect_e(BAR(B_WMFULL), gemv ? 28672 >> early : 0);
                if (early && gemv) { tma3_e(wmbuf, &p.wm, mcol, 0, 0, BAR(B_WMFULL)); tma3_e(wmbuf + 7168, &p.wm, mcol, 224, 0, BAR(B_WMFULL)); }
#pragma unroll 1
                for (int kb = 0; kb < 7; kb++) {
                    expect_e(BAR(B_XFULL + kb), 16384);
                    tma3_e(sb + OFF_X + kb * 16384, &p.xm, 64 * kb, 128 * r, 0, BAR(B_XFULL + kb));
                }
            }
#pragma unroll 1
            for (int mt = 0; mt < 4; mt++) {
                if (mt == 1) {
                    if (!early && gemv) {
#pragma unroll 1
                        for (int k = 0; k < 4; k++) tma3_e(wmbuf + k * 7168, &p.wm, mcol + (k >> 1) * 16, (k & 1) * 224, 0, BAR(B_WMFULL));
                    }
                    bar_sync(9, 384);
                    if (sc) return;
                    mbar_wait(BAR(B_MOD1), 0);
                    mbar_wait(BAR(B_WMFREE), 0);
                }
                if (mt == 2) mbar_wait(BAR(B_XFREE), 0);
                if (mt == 3) mbar_wait(BAR(B_VRFULL), 0);
                const uint32_t bar = BAR(mt == 3 ? B_WOFULL : B_FULLK + mt), dst = sb + (mt < 2 ? OFF_Y : OFF_X) + (mt & 1) * HALF;
                const int c0 = (mt < 2 ? DM + DM * mt : 0) + 56 * j - 8 * kh;
                if (!sc) {
                    expect_e(bar, HALF);
                    tma3_e(dst, mt == 3 ? &p.wo : &p.qkv, c0, 0, 0, bar);
                    tma3_e(dst + HALF / 2, mt == 3 ? &p.wo : &p.qkv, c0, 224, 0, bar);
                }
            }
            expect_e(BAR(B_XCH), 14336);
            expect_e(BAR(B_XCH + 1), 14336);
        } else {
            if (warp == 10 && !sc) {
                l2_prefetch_e((const char*)p.wqkv + (size_t)b * 9408, 9408);
                if (lane == 0) sts1(sb + M_EPOCH, atomicAdd(&g_ticket, 1u) / NCTA);
            }
            if (warp == 11) {
#pragma unroll
                for (int i = 0; i < 8; i++) {
                    const int wd = lane + 32 * i;
                    const uint32_t cb = i < 7 ? __ldg((const uint32_t*)p.c + wd) : 0u;
                    sts1(wmbuf + 28672 + (wd >> 3) * 32 + (wd & 3) * 8 + (wd & 4), pack2(silu_bf(cb & 0xFFFFu), silu_bf(cb >> 16)));
                }
            }
            bar_sync(9, 384);
            if (sc) return;
            target = lds1(sb + M_EPOCH) + 1;
            const uint32_t tag = target & 0xFFFFu;
            if (warp == 11) {
                warp_arrive(BAR(B_WMFULL));
                mbar_wait(BAR(B_GEMV), 0);
                float sum = 0.f;
#pragma unroll
                for (int i = 0; i < 8; i++) sum += *(const float*)(smem + OFF_Y + HALF + 29696 + (i * 32 + (early ? lane & 15 : lane)) * 4);
                const uint32_t word = (pack2(sum, 0.f) << 16) | tag;
                if (gemv) {
                    uint32_t* mg = g_mod + mcol + (early ? (lane & 15) + (lane >> 4) * 4 * 6 * DM : lane);
#pragma unroll
                    for (int i = 0; i < 8; i++) if (i < 4 || !early) st_relaxed(mg + i * 6 * DM, word);
                }
                warp_arrive(BAR(B_WMFREE));
            }
            const uint4* modp = (const uint4*)g_mod + (r & 7) * (6 * DM / 4);
            const bool p2 = warp == 11;
            mbar_wait(BAR(p2 ? B_PUB : B_XFULL + 4), 0);
#pragma unroll 1
            for (int it = p2 ? 0 : warp - 9; it < (p2 ? 2 : warp - 8); it++) {
                const int i0 = lane + 32 * it, imax = p2 ? 251 : 223;
                uint4 v[4];
#pragma unroll 1
                for (int n = 0;; n++) {
                    uint32_t bad = 0;
#pragma unroll
                    for (int k = 0; k < 4; k++) {
                        const int i = min(i0 + 64 * k, imax);
                        v[k] = ld_relaxed4(modp + (i < 224 ? (p2 ? 336 : 0) + i : (i < 238 ? 14 * j + i : 14 * j + i + 322)));
                        bad |= (v[k].x ^ tag) | (v[k].y ^ tag) | (v[k].z ^ tag) | (v[k].w ^ tag);
                    }
                    if (!__any_sync(~0u, bad & 0xFFFFu)) break;
                    if (n > SPIN_LIMIT) __trap();
                }
#pragma unroll
                for (int k = 0; k < 4; k++) {
                    const int i = min(i0 + 64 * k, imax);
                    if (i < 224) {
                        const int isc = i >= 112, c4 = i - 112 * isc;
                        const float one = isc ? 1.f : 0.f;
                        const uint32_t a = sb + M_ST + (c4 >> 2) * 64 + (c4 & 1) * 32 + (c4 & 2) * 4 + (isc ? 0 : 4);
                        sts1(a, pack2(bf_hi(v[k].x) + one, bf_hi(v[k].y) + one));
                        sts1(a + 16, pack2(bf_hi(v[k].z) + one, bf_hi(v[k].w) + one));
                    } else {
                        sts4(sb + M_G + (i - 224) * 16, make_uint4(v[k].x & 0xFFFF0000u, v[k].y & 0xFFFF0000u, v[k].z & 0xFFFF0000u, v[k].w & 0xFFFF0000u));
                    }
                }
                warp_arrive(BAR(p2 ? B_MOD2 : B_MOD1));
            }
            if (warp == 9) {
#pragma unroll 1
                for (int kv = 0; kv < 2; kv++) {
                    mbar_wait(BAR(B_PUB + kv), 0);
                    if (lane >= 1 && lane <= 2 && r >= lane) wait_flag(g_flag + b * 96 + kv * 8 + lane, target);
                    __syncwarp();
                    fence_async_global();
                    const uint32_t dst = sb + OFF_Y + (kv ? Y_VR : Y_K);
                    expect_e(BAR(B_KRFULL + kv), r >= 2 ? 28672 : r == 1 ? 14336 : 0);
                    if (r >= 2) bulk_e(dst, g_kv + (size_t)((b - 16) * 2 + kv) * 3584, 14336, BAR(B_KRFULL + kv));
                    if (r >= 1) bulk_e(dst + 14336, g_kv + (size_t)((b - 8) * 2 + kv) * 3584, 14336, BAR(B_KRFULL + kv));
                }
            } else if (warp == 11) {
                mbar_wait(BAR(B_VRFULL), 0);
                l2_prefetch_e((const char*)p.wg + (size_t)b * 12544, 12544);
                l2_prefetch_e((const char*)p.wu + (size_t)b * 12544, 12544);
                l2_prefetch_e((const char*)p.wd + (size_t)b * 12544, 12544);
            }
        }
        if (warp == 8 || warp == 11) {
            const int sec = warp == 11;
            if (sec) ring_loader<1>(p, sb, r, j); else ring_loader<0>(p, sb, r, j);
            mbar_wait(BAR(B_DONE), 0);
        } else if (warp == 9) {
#pragma unroll
            for (int ev = 0; ev < 4; ev++) expect_e(BAR(B_GFULL + ev), ev < 2 ? HALF : HALF + 4096);
            mbar_wait(BAR(B_PUB + 2), 0);
            const uint32_t* fp = g_flag + b * 96 + 32 + lane;
            const uint32_t* src = g_ox + (size_t)2 * r * 14336;
            const float2* ssrc = g_st + 2 * r * 512;
#pragma unroll 1
            for (int n = 0, ev = 0; ev < 4; n++) {
                if (ev == 1) mbar_wait(BAR(B_PUB + 3), 0);
                uint32_t ok = __ballot_sync(~0u, (int)(ld_relaxed(fp) - target) >= 0) >> (8 * ev);
                while ((ok & 0xFFu) == 0xFFu) {
                    asm volatile("fence.acquire.gpu;" ::: "memory");
                    fence_async_global();
                    const uint32_t bar = BAR(B_GFULL + ev);
                    bulk_e(sb + (ev == 0 ? OFF_X : OFF_Y + (ev & 1) * HALF), src + (ev >> 1) * (34 * 14336) + (ev & 1) * 14336, HALF, bar);
                    if (ev >= 2) bulk_e(sb + OFF_X + X_STAT + (ev & 1) * 4096, ssrc + (ev & 1) * 512, 4096, bar);
                    if (ev) PROFH(4 + ev);
                    ev++; ok >>= 8;
                }
                if (n > SPIN_LIMIT) __trap();
            }
#pragma unroll 1
            for (int ps = 0; ps < 3; ps++) {
                mbar_wait(BAR(B_PUB + 6 + ps), 0);
                if (lane < 4) wait_flag(g_flag + b * 96 + 64 + ps * 8 + 2 * lane + kh, target);
                warp_arrive(BAR(B_HRDY + ps));
                PROFH(9 + ps);
            }
        } else {
#pragma unroll 1
            for (int k = 0; k < 9; k++) {
                uint32_t* fp = k < 2 ? g_flag + (b + 8 * lane) * 96 + k * 8 + lane : g_flag + (8 * r + lane) * 96 + 16 + k * 8 + j;
                mbar_wait(BAR(B_PUB + k), 0);
                if (k < 2 ? (lane == 1 || lane == 2) : lane < 8) {
                    fence_gpu();
                    st_relaxed(fp, target);
                }
                __syncwarp();
                if (k >= 3 && k <= 5) PROFH(k - 3);
            }
        }
    }
}

typedef CUresult (*EncodeFn)(CUtensorMap*, CUtensorMapDataType, cuuint32_t, void*, const cuuint64_t*, const cuuint64_t*, const cuuint32_t*,
                             const cuuint32_t*, CUtensorMapInterleave, CUtensorMapSwizzle, CUtensorMapL2promotion, CUtensorMapFloatOOBfill);

static void make_map(EncodeFn fn, CUtensorMap* m, const void* ptr, uint64_t d0, uint64_t d1, uint64_t d2, uint64_t s1, uint64_t s2,
                     uint32_t b0, uint32_t b1, uint32_t b2, CUtensorMapSwizzle sw) {
    cuuint64_t dims[3] = {d0, d1, d2}, strides[2] = {s1, s2};
    cuuint32_t box[3] = {b0, b1, b2}, es[3] = {1, 1, 1};
    CUresult rc = fn(m, CU_TENSOR_MAP_DATA_TYPE_BFLOAT16, 3, (void*)ptr, dims, strides, box, es, CU_TENSOR_MAP_INTERLEAVE_NONE, sw,
                     CU_TENSOR_MAP_L2_PROMOTION_L2_128B, CU_TENSOR_MAP_FLOAT_OOB_FILL_NONE);
    (void)rc;
}

extern "C" void kernel_launch(void* const* d_in, const int* in_sizes, int n_in, void* d_out, int out_size) {
    (void)in_sizes; (void)n_in; (void)out_size;
    static EncodeFn fn = nullptr;
    if (!fn) {
        cudaDriverEntryPointQueryResult st;
        cudaGetDriverEntryPoint("cuTensorMapEncodeTiled", (void**)&fn, cudaEnableDefault, &st);
        cudaFuncSetAttribute(fused_block_kernel, cudaFuncAttributeMaxDynamicSharedMemorySize, SMEM_BYTES);
    }
    Params p;
    p.x = (const bf16*)d_in[0];
    const bf16* wqkv = (const bf16*)d_in[1];
    p.wqkv = wqkv;
    p.wop = (const bf16*)d_in[2];
    p.wg = (const bf16*)d_in[4];
    p.wu = (const bf16*)d_in[5];
    p.wd = (const bf16*)d_in[6];
    p.c = (const bf16*)d_in[7];
    p.wmod = (const bf16*)d_in[8];
    p.out = (bf16*)d_out;
    p.zero = 0;
    make_map(fn, &p.wm, p.wmod, 2688, 448, 1, 5376, 5376 * 448, 16, 224, 1, CU_TENSOR_MAP_SWIZZLE_NONE);
    make_map(fn, &p.xm, p.x, 448, 2048, 1, 896, 896 * 2048, 64, 128, 1, CU_TENSOR_MAP_SWIZZLE_128B);
    make_map(fn, &p.qkv, wqkv, 1344, 448, 1, 2688, 2688 * 448, 64, 224, 1, CU_TENSOR_MAP_SWIZZLE_128B);
    make_map(fn, &p.wo, p.wop, 448, 448, 1, 896, 896 * 448, 64, 224, 1, CU_TENSOR_MAP_SWIZZLE_128B);
    make_map(fn, &p.ga, p.wg, 64, 448, 28, 3584, 128, 64, 32, 2, CU_TENSOR_MAP_SWIZZLE_128B);
    make_map(fn, &p.ua, p.wu, 64, 448, 28, 3584, 128, 64, 32, 2, CU_TENSOR_MAP_SWIZZLE_128B);
    make_map(fn, &p.gb, p.wg, 64, 448, 28, 3584, 128, 64, 64, 1, CU_TENSOR_MAP_SWIZZLE_128B);
    make_map(fn, &p.ub, p.wu, 64, 448, 28, 3584, 128, 64, 64, 1, CU_TENSOR_MAP_SWIZZLE_128B);
    make_map(fn, &p.gc, p.wg, 32, 448, 56, 3584, 64, 32, 64, 1, CU_TENSOR_MAP_SWIZZLE_64B);
    make_map(fn, &p.uc, p.wu, 32, 448, 56, 3584, 64, 32, 64, 1, CU_TENSOR_MAP_SWIZZLE_64B);
    make_map(fn, &p.dn, p.wd, 448, 1792, 1, 896, 896 * 1792, 64, 32, 1, CU_TENSOR_MAP_SWIZZLE_128B);
    fused_block_kernel<<<GRID, 384, SMEM_BYTES>>>(p);
}
```

```cpp
#include <cuda_runtime.h>
#include <cuda_bf16.h>
#include <cuda.h>
#include <stdint.h>

typedef __nv_bfloat16 bf16;

template<uint64_t CB> __device__ __forceinline__ void wgmma_rs_56(float* d, uint32_t a0, uint32_t a1, uint32_t a2, uint32_t a3, uint32_t db, int sd) {
  asm volatile("{\n.reg .pred p;\n.reg .b64 b;\nsetp.ne.b32 p, %33, 0;\nmov.b64 b, {%32, %34};\n"
    "wgmma.mma_async.sync.aligned.m64n56k16.f32.bf16.bf16 {%0,%1,%2,%3,%4,%5,%6,%7,%8,%9,%10,%11,%12,%13,%14,%15,%16,%17,%18,%19,%20,%21,%22,%23,%24,%25,%26,%27}, {%28,%29,%30,%31}, b, p, 1, 1, 1;\n}\n"
    : "+f"(d[0]),"+f"(d[1]),"+f"(d[2]),"+f"(d[3]),"+f"(d[4]),"+f"(d[5]),"+f"(d[6]),"+f"(d[7]),"+f"(d[8]),"+f"(d[9]),"+f"(d[10]),"+f"(d[11]),"+f"(d[12]),"+f"(d[13]),"+f"(d[14]),"+f"(d[15]),"+f"(d[16]),"+f"(d[17]),"+f"(d[18]),"+f"(d[19]),"+f"(d[20]),"+f"(d[21]),"+f"(d[22]),"+f"(d[23]),"+f"(d[24]),"+f"(d[25]),"+f"(d[26]),"+f"(d[27])
    : "r"(a0), "r"(a1), "r"(a2), "r"(a3), "r"(db), "r"(sd), "n"((uint32_t)(CB >> 32)));
}
template<uint64_t CA, uint64_t CB> __device__ __forceinline__ void wgmma_ss_56(float* d, uint32_t da, uint32_t db, int sd) {
  asm volatile("{\n.reg .pred p;\n.reg .b64 a, b;\nsetp.ne.b32 p, %30, 0;\nmov.b64 a, {%28, %31};\nmov.b64 b, {%29, %32};\n"
    "wgmma.mma_async.sync.aligned.m64n56k16.f32.bf16.bf16 {%0,%1,%2,%3,%4,%5,%6,%7,%8,%9,%10,%11,%12,%13,%14,%15,%16,%17,%18,%19,%20,%21,%22,%23,%24,%25,%26,%27}, a, b, p, 1, 1, 0, 1;\n}\n"
    : "+f"(d[0]),"+f"(d[1]),"+f"(d[2]),"+f"(d[3]),"+f"(d[4]),"+f"(d[5]),"+f"(d[6]),"+f"(d[7]),"+f"(d[8]),"+f"(d[9]),"+f"(d[10]),"+f"(d[11]),"+f"(d[12]),"+f"(d[13]),"+f"(d[14]),"+f"(d[15]),"+f"(d[16]),"+f"(d[17]),"+f"(d[18]),"+f"(d[19]),"+f"(d[20]),"+f"(d[21]),"+f"(d[22]),"+f"(d[23]),"+f"(d[24]),"+f"(d[25]),"+f"(d[26]),"+f"(d[27])
    : "r"(da), "r"(db), "r"(sd), "n"((uint32_t)(CA >> 32)), "n"((uint32_t)(CB >> 32)));
}
template<uint64_t CB> __device__ __forceinline__ void wgmma_rs_256(float* d, uint32_t a0, uint32_t a1, uint32_t a2, uint32_t a3, uint32_t db, int sd) {
  asm volatile("{\n.reg .pred p;\n.reg .b64 b;\nsetp.ne.b32 p, %133, 0;\nmov.b64 b, {%132, %134};\n"
    "wgmma.mma_async.sync.aligned.m64n256k16.f32.bf16.bf16 {%0,%1,%2,%3,%4,%5,%6,%7,%8,%9,%10,%11,%12,%13,%14,%15,%16,%17,%18,%19,%20,%21,%22,%23,%24,%25,%26,%27,%28,%29,%30,%31,%32,%33,%34,%35,%36,%37,%38,%39,%40,%41,%42,%43,%44,%45,%46,%47,%48,%49,%50,%51,%52,%53,%54,%55,%56,%57,%58,%59,%60,%61,%62,%63,%64,%65,%66,%67,%68,%69,%70,%71,%72,%73,%74,%75,%76,%77,%78,%79,%80,%81,%82,%83,%84,%85,%86,%87,%88,%89,%90,%91,%92,%93,%94,%95,%96,%97,%98,%99,%100,%101,%102,%103,%104,%105,%106,%107,%108,%109,%110,%111,%112,%113,%114,%115,%116,%117,%118,%119,%120,%121,%122,%123,%124,%125,%126,%127}, {%128,%129,%130,%131}, b, p, 1, 1, 1;\n}\n"
    : "+f"(d[0]),"+f"(d[1]),"+f"(d[2]),"+f"(d[3]),"+f"(d[4]),"+f"(d[5]),"+f"(d[6]),"+f"(d[7]),"+f"(d[8]),"+f"(d[9]),"+f"(d[10]),"+f"(d[11]),"+f"(d[12]),"+f"(d[13]),"+f"(d[14]),"+f"(d[15]),"+f"(d[16]),"+f"(d[17]),"+f"(d[18]),"+f"(d[19]),"+f"(d[20]),"+f"(d[21]),"+f"(d[22]),"+f"(d[23]),"+f"(d[24]),"+f"(d[25]),"+f"(d[26]),"+f"(d[27]),"+f"(d[28]),"+f"(d[29]),"+f"(d[30]),"+f"(d[31]),"+f"(d[32]),"+f"(d[33]),"+f"(d[34]),"+f"(d[35]),"+f"(d[36]),"+f"(d[37]),"+f"(d[38]),"+f"(d[39]),"+f"(d[40]),"+f"(d[41]),"+f"(d[42]),"+f"(d[43]),"+f"(d[44]),"+f"(d[45]),"+f"(d[46]),"+f"(d[47]),"+f"(d[48]),"+f"(d[49]),"+f"(d[50]),"+f"(d[51]),"+f"(d[52]),"+f"(d[53]),"+f"(d[54]),"+f"(d[55]),"+f"(d[56]),"+f"(d[57]),"+f"(d[58]),"+f"(d[59]),"+f"(d[60]),"+f"(d[61]),"+f"(d[62]),"+f"(d[63]),"+f"(d[64]),"+f"(d[65]),"+f"(d[66]),"+f"(d[67]),"+f"(d[68]),"+f"(d[69]),"+f"(d[70]),"+f"(d[71]),"+f"(d[72]),"+f"(d[73]),"+f"(d[74]),"+f"(d[75]),"+f"(d[76]),"+f"(d[77]),"+f"(d[78]),"+f"(d[79]),"+f"(d[80]),"+f"(d[81]),"+f"(d[82]),"+f"(d[83]),"+f"(d[84]),"+f"(d[85]),"+f"(d[86]),"+f"(d[87]),"+f"(d[88]),"+f"(d[89]),"+f"(d[90]),"+f"(d[91]),"+f"(d[92]),"+f"(d[93]),"+f"(d[94]),"+f"(d[95]),"+f"(d[96]),"+f"(d[97]),"+f"(d[98]),"+f"(d[99]),"+f"(d[100]),"+f"(d[101]),"+f"(d[102]),"+f"(d[103]),"+f"(d[104]),"+f"(d[105]),"+f"(d[106]),"+f"(d[107]),"+f"(d[108]),"+f"(d[109]),"+f"(d[110]),"+f"(d[111]),"+f"(d[112]),"+f"(d[113]),"+f"(d[114]),"+f"(d[115]),"+f"(d[116]),"+f"(d[117]),"+f"(d[118]),"+f"(d[119]),"+f"(d[120]),"+f"(d[121]),"+f"(d[122]),"+f"(d[123]),"+f"(d[124]),"+f"(d[125]),"+f"(d[126]),"+f"(d[127])
    : "r"(a0), "r"(a1), "r"(a2), "r"(a3), "r"(db), "r"(sd), "n"((uint32_t)(CB >> 32)));
}
template<uint64_t CA, uint64_t CB> __device__ __forceinline__ void wgmma_ss_128(float* d, uint32_t da, uint32_t db, int sd) {
  asm volatile("{\n.reg .pred p;\n.reg .b64 a, b;\nsetp.ne.b32 p, %66, 0;\nmov.b64 a, {%64, %67};\nmov.b64 b, {%65, %68};\n"
    "wgmma.mma_async.sync.aligned.m64n128k16.f32.bf16.bf16 {%0,%1,%2,%3,%4,%5,%6,%7,%8,%9,%10,%11,%12,%13,%14,%15,%16,%17,%18,%19,%20,%21,%22,%23,%24,%25,%26,%27,%28,%29,%30,%31,%32,%33,%34,%35,%36,%37,%38,%39,%40,%41,%42,%43,%44,%45,%46,%47,%48,%49,%50,%51,%52,%53,%54,%55,%56,%57,%58,%59,%60,%61,%62,%63}, a, b, p, 1, 1, 0, 1;\n}\n"
    : "+f"(d[0]),"+f"(d[1]),"+f"(d[2]),"+f"(d[3]),"+f"(d[4]),"+f"(d[5]),"+f"(d[6]),"+f"(d[7]),"+f"(d[8]),"+f"(d[9]),"+f"(d[10]),"+f"(d[11]),"+f"(d[12]),"+f"(d[13]),"+f"(d[14]),"+f"(d[15]),"+f"(d[16]),"+f"(d[17]),"+f"(d[18]),"+f"(d[19]),"+f"(d[20]),"+f"(d[21]),"+f"(d[22]),"+f"(d[23]),"+f"(d[24]),"+f"(d[25]),"+f"(d[26]),"+f"(d[27]),"+f"(d[28]),"+f"(d[29]),"+f"(d[30]),"+f"(d[31]),"+f"(d[32]),"+f"(d[33]),"+f"(d[34]),"+f"(d[35]),"+f"(d[36]),"+f"(d[37]),"+f"(d[38]),"+f"(d[39]),"+f"(d[40]),"+f"(d[41]),"+f"(d[42]),"+f"(d[43]),"+f"(d[44]),"+f"(d[45]),"+f"(d[46]),"+f"(d[47]),"+f"(d[48]),"+f"(d[49]),"+f"(d[50]),"+f"(d[51]),"+f"(d[52]),"+f"(d[53]),"+f"(d[54]),"+f"(d[55]),"+f"(d[56]),"+f"(d[57]),"+f"(d[58]),"+f"(d[59]),"+f"(d[60]),"+f"(d[61]),"+f"(d[62]),"+f"(d[63])
    : "r"(da), "r"(db), "r"(sd), "n"((uint32_t)(CA >> 32)), "n"((uint32_t)(CB >> 32)));
}
template<uint64_t CA, uint64_t CB> __device__ __forceinline__ void wgmma_ss_64(float* d, uint32_t da, uint32_t db, int sd) {
  asm volatile("{\n.reg .pred p;\n.reg .b64 a, b;\nsetp.ne.b32 p, %34, 0;\nmov.b64 a, {%32, %35};\nmov.b64 b, {%33, %36};\n"
    "wgmma.mma_async.sync.aligned.m64n64k16.f32.bf16.bf16 {%0,%1,%2,%3,%4,%5,%6,%7,%8,%9,%10,%11,%12,%13,%14,%15,%16,%17,%18,%19,%20,%21,%22,%23,%24,%25,%26,%27,%28,%29,%30,%31}, a, b, p, 1, 1, 0, 1;\n}\n"
    : "+f"(d[0]),"+f"(d[1]),"+f"(d[2]),"+f"(d[3]),"+f"(d[4]),"+f"(d[5]),"+f"(d[6]),"+f"(d[7]),"+f"(d[8]),"+f"(d[9]),"+f"(d[10]),"+f"(d[11]),"+f"(d[12]),"+f"(d[13]),"+f"(d[14]),"+f"(d[15]),"+f"(d[16]),"+f"(d[17]),"+f"(d[18]),"+f"(d[19]),"+f"(d[20]),"+f"(d[21]),"+f"(d[22]),"+f"(d[23]),"+f"(d[24]),"+f"(d[25]),"+f"(d[26]),"+f"(d[27]),"+f"(d[28]),"+f"(d[29]),"+f"(d[30]),"+f"(d[31])
    : "r"(da), "r"(db), "r"(sd), "n"((uint32_t)(CA >> 32)), "n"((uint32_t)(CB >> 32)));
}
template<uint64_t CA, uint64_t CB> __device__ __forceinline__ void wgmma_ss_112(float* d, uint32_t da, uint32_t db, int sd) {
  asm volatile("{\n.reg .pred p;\n.reg .b64 a, b;\nsetp.ne.b32 p, %58, 0;\nmov.b64 a, {%56, %59};\nmov.b64 b, {%57, %60};\n"
    "wgmma.mma_async.sync.aligned.m64n112k16.f32.bf16.bf16 {%0,%1,%2,%3,%4,%5,%6,%7,%8,%9,%10,%11,%12,%13,%14,%15,%16,%17,%18,%19,%20,%21,%22,%23,%24,%25,%26,%27,%28,%29,%30,%31,%32,%33,%34,%35,%36,%37,%38,%39,%40,%41,%42,%43,%44,%45,%46,%47,%48,%49,%50,%51,%52,%53,%54,%55}, a, b, p, 1, 1, 0, 1;\n}\n"
    : "+f"(d[0]),"+f"(d[1]),"+f"(d[2]),"+f"(d[3]),"+f"(d[4]),"+f"(d[5]),"+f"(d[6]),"+f"(d[7]),"+f"(d[8]),"+f"(d[9]),"+f"(d[10]),"+f"(d[11]),"+f"(d[12]),"+f"(d[13]),"+f"(d[14]),"+f"(d[15]),"+f"(d[16]),"+f"(d[17]),"+f"(d[18]),"+f"(d[19]),"+f"(d[20]),"+f"(d[21]),"+f"(d[22]),"+f"(d[23]),"+f"(d[24]),"+f"(d[25]),"+f"(d[26]),"+f"(d[27]),"+f"(d[28]),"+f"(d[29]),"+f"(d[30]),"+f"(d[31]),"+f"(d[32]),"+f"(d[33]),"+f"(d[34]),"+f"(d[35]),"+f"(d[36]),"+f"(d[37]),"+f"(d[38]),"+f"(d[39]),"+f"(d[40]),"+f"(d[41]),"+f"(d[42]),"+f"(d[43]),"+f"(d[44]),"+f"(d[45]),"+f"(d[46]),"+f"(d[47]),"+f"(d[48]),"+f"(d[49]),"+f"(d[50]),"+f"(d[51]),"+f"(d[52]),"+f"(d[53]),"+f"(d[54]),"+f"(d[55])
    : "r"(da), "r"(db), "r"(sd), "n"((uint32_t)(CA >> 32)), "n"((uint32_t)(CB >> 32)));
}
template<uint64_t CB> __device__ __forceinline__ void wgmma_rs_112(float* d, uint32_t a0, uint32_t a1, uint32_t a2, uint32_t a3, uint32_t db, int sd) {
  asm volatile("{\n.reg .pred p;\n.reg .b64 b;\nsetp.ne.b32 p, %61, 0;\nmov.b64 b, {%60, %62};\n"
    "wgmma.mma_async.sync.aligned.m64n112k16.f32.bf16.bf16 {%0,%1,%2,%3,%4,%5,%6,%7,%8,%9,%10,%11,%12,%13,%14,%15,%16,%17,%18,%19,%20,%21,%22,%23,%24,%25,%26,%27,%28,%29,%30,%31,%32,%33,%34,%35,%36,%37,%38,%39,%40,%41,%42,%43,%44,%45,%46,%47,%48,%49,%50,%51,%52,%53,%54,%55}, {%56,%57,%58,%59}, b, p, 1, 1, 1;\n}\n"
    : "+f"(d[0]),"+f"(d[1]),"+f"(d[2]),"+f"(d[3]),"+f"(d[4]),"+f"(d[5]),"+f"(d[6]),"+f"(d[7]),"+f"(d[8]),"+f"(d[9]),"+f"(d[10]),"+f"(d[11]),"+f"(d[12]),"+f"(d[13]),"+f"(d[14]),"+f"(d[15]),"+f"(d[16]),"+f"(d[17]),"+f"(d[18]),"+f"(d[19]),"+f"(d[20]),"+f"(d[21]),"+f"(d[22]),"+f"(d[23]),"+f"(d[24]),"+f"(d[25]),"+f"(d[26]),"+f"(d[27]),"+f"(d[28]),"+f"(d[29]),"+f"(d[30]),"+f"(d[31]),"+f"(d[32]),"+f"(d[33]),"+f"(d[34]),"+f"(d[35]),"+f"(d[36]),"+f"(d[37]),"+f"(d[38]),"+f"(d[39]),"+f"(d[40]),"+f"(d[41]),"+f"(d[42]),"+f"(d[43]),"+f"(d[44]),"+f"(d[45]),"+f"(d[46]),"+f"(d[47]),"+f"(d[48]),"+f"(d[49]),"+f"(d[50]),"+f"(d[51]),"+f"(d[52]),"+f"(d[53]),"+f"(d[54]),"+f"(d[55])
    : "r"(a0), "r"(a1), "r"(a2), "r"(a3), "r"(db), "r"(sd), "n"((uint32_t)(CB >> 32)));
}

constexpr int DM = 448;
constexpr int NCTA = 128;
#define MAPPING 1
#define GRID 132
#define PINGPONG 0
#define WIN 4
#define WIN_END 25
#define UNR_G2 21
#define UNR_B 7
#define UNR_C 7
constexpr int kG2 = UNR_G2, kB = UNR_B, kC = UNR_C;
#define MAP_S 4
constexpr int SPIN_LIMIT = 1 << 22;

constexpr uint32_t OFF_X = 0, OFF_Y = 114688, OFF_MISC = 229376, SMEM_BYTES = 232448;
constexpr uint32_t Y_VR = 0, Y_K = 28672, Y_KOWN = 57344, Y_VOWN = 71680, Y_Q = 86016;
constexpr uint32_t HALF = 57344;
constexpr uint32_t M_BAR = OFF_MISC;
constexpr uint32_t M_ST = OFF_MISC + 512;
constexpr uint32_t M_G = OFF_MISC + 2304;
constexpr uint32_t M_EPOCH = OFF_MISC + 3040;
enum { B_XFULL = 0, B_FULLK = 7, B_FULLV = 8, B_FULLQ, B_KRFULL, B_VRFULL, B_WOFULL, B_XCH, B_FULL = 16, B_MOD1 = 28, B_MOD2, B_WMFULL,
       B_EMPTY = 32, B_XFREE = B_EMPTY + 12, B_GEMV, B_PEER,
       B_PUB = 47,
       B_WMFREE = 56, B_HRDY, B_GFULL = B_HRDY + 3, B_DONE = 31 };
constexpr uint32_t X_STAT = 49152;

__device__ uint32_t g_ticket;
__device__ __align__(128) uint32_t g_mod[8 * 6 * DM];
__device__ __align__(128) uint32_t g_flag[144 * 96];
__device__ __align__(128) uint32_t g_kv[17 * 8 * 2 * 3584];
__device__ __align__(128) uint32_t g_ox[2 * 34 * 14336];
#define g_o g_ox
#define g_x1 (g_ox + 34 * 14336)
__device__ __align__(128) float2 g_st[34 * 8 * 64];
__device__ __align__(128) uint32_t g_h2[17 * 224 * 512];
#define PROFH(id)
#define PROFH1(id)
#define PROFC(id)

struct alignas(64) Params {
    CUtensorMap wm, xm, qkv, wo, ga, ua, gb, ub, gc, uc, dn;
    const bf16 *x, *c, *wqkv, *wmod, *wg, *wu, *wd, *wop;
    bf16* out;
    uint32_t zero;
};

__device__ __forceinline__ void mbar_init(uint32_t bar, int cnt) { asm volatile("mbarrier.init.shared::cta.b64 [%0], %1;" ::"r"(bar), "r"(cnt) : "memory"); }
__device__ __forceinline__ void mbar_expect_tx(uint32_t bar, uint32_t bytes) { asm volatile("mbarrier.arrive.expect_tx.shared::cta.b64 _, [%0], %1;" ::"r"(bar), "r"(bytes) : "memory"); }
__device__ __forceinline__ void mbar_arrive(uint32_t bar) { asm volatile("mbarrier.arrive.shared::cta.b64 _, [%0];" ::"r"(bar) : "memory"); }
__device__ __forceinline__ void mbar_wait(uint32_t bar, uint32_t parity) {
    uint32_t ok; int n = 0;
    do {
        asm volatile("{\n.reg .pred p;\nmbarrier.try_wait.parity.shared::cta.b64 p, [%1], %2;\nselp.u32 %0, 1, 0, p;\n}" : "=r"(ok) : "r"(bar), "r"(parity) : "memory");
        if (++n > SPIN_LIMIT) __trap();
    } while (!ok);
}
__device__ __forceinline__ void mbar_wait_c(uint32_t bar, uint32_t parity) {
    asm volatile("{\n.reg .pred p;\nWL:\nmbarrier.try_wait.parity.shared::cta.b64 p, [%0], %1;\n@!p bra WL;\n}" ::"r"(bar), "r"(parity) : "memory");
}
__device__ __forceinline__ void mbar_wait_cluster(uint32_t bar, uint32_t parity) {
    uint32_t ok; int n = 0;
    do {
        asm volatile("{\n.reg .pred p;\nmbarrier.try_wait.parity.acquire.cluster.shared::cta.b64 p, [%1], %2;\nselp.u32 %0, 1, 0, p;\n}" : "=r"(ok) : "r"(bar), "r"(parity) : "memory");
        if (++n > SPIN_LIMIT) __trap();
    } while (!ok);
}
__device__ __forceinline__ void warp_arrive(uint32_t bar) {
    __syncwarp();
    asm volatile("{\n.reg .pred p;\nelect.sync _|p, 0xffffffff;\n@p mbarrier.arrive.shared::cta.b64 _, [%0];\n}" ::"r"(bar) : "memory");
}
__device__ __forceinline__ int opaque(int v) { return __shfl_sync(~0u, v, 0); }
__device__ __forceinline__ int fresh_tid() { int v; asm volatile("mov.u32 %0, %%tid.x;" : "=r"(v)); return v; }
__device__ __forceinline__ void bar_sync(int id, int n) { asm volatile("bar.sync %0, %1;" ::"r"(id), "r"(n) : "memory"); }
__device__ __forceinline__ void bar_arrive(int id, int n) { asm volatile("bar.arrive %0, %1;" ::"r"(id), "r"(n) : "memory"); }
__device__ __forceinline__ void fence_async_smem() { asm volatile("fence.proxy.async.shared::cta;" ::: "memory"); }
__device__ __forceinline__ void fence_async_global() { asm volatile("fence.proxy.async.global;" ::: "memory"); }
__device__ __forceinline__ void fence_gpu() { asm volatile("fence.release.gpu;" ::: "memory"); }
__device__ __forceinline__ void tma3(uint32_t dst, const CUtensorMap* m, int c0, int c1, int c2, uint32_t bar) {
    asm volatile("cp.async.bulk.tensor.3d.shared::cluster.global.mbarrier::complete_tx::bytes [%0], [%1, {%3, %4, %5}], [%2];"
                 ::"r"(dst), "l"(m), "r"(bar), "r"(c0), "r"(c1), "r"(c2) : "memory");
}
__device__ __forceinline__ void bulk_load(uint32_t dst, const void* src, uint32_t bytes, uint32_t bar) {
    asm volatile("cp.async.bulk.shared::cluster.global.mbarrier::complete_tx::bytes [%0], [%1], %2, [%3];" ::"r"(dst), "l"(src), "r"(bytes), "r"(bar) : "memory");
}
__device__ __forceinline__ void expect_e(uint32_t bar, uint32_t bytes) {
    asm volatile("{\n.reg .pred p;\nelect.sync _|p, 0xffffffff;\n@p mbarrier.arrive.expect_tx.shared::cta.b64 _, [%0], %1;\n}" ::"r"(bar), "r"(bytes) : "memory");
}
__device__ __forceinline__ void tma3_e(uint32_t dst, const CUtensorMap* m, int c0, int c1, int c2, uint32_t bar) {
    asm volatile("{\n.reg .pred p;\nelect.sync _|p, 0xffffffff;\n@p cp.async.bulk.tensor.3d.shared::cluster.global.mbarrier::complete_tx::bytes [%0], [%1, {%3, %4, %5}], [%2];\n}"
                 ::"r"(dst), "l"(m), "r"(bar), "r"(c0), "r"(c1), "r"(c2) : "memory");
}
__device__ __forceinline__ void bulk_e(uint32_t dst, const void* src, uint32_t bytes, uint32_t bar) {
    asm volatile("{\n.reg .pred p;\nelect.sync _|p, 0xffffffff;\n@p cp.async.bulk.shared::cluster.global.mbarrier::complete_tx::bytes [%0], [%1], %2, [%3];\n}"
                 ::"r"(dst), "l"(src), "r"(bytes), "r"(bar) : "memory");
}
__device__ __forceinline__ void init_e(uint32_t bar, int cnt) {
    asm volatile("{\n.reg .pred p;\nelect.sync _|p, 0xffffffff;\n@p mbarrier.init.shared::cta.b64 [%0], %1;\n}" ::"r"(bar), "r"(cnt) : "memory");
}
__device__ __forceinline__ void l2_prefetch_e(const void* src, uint32_t bytes) {
    asm volatile("{\n.reg .pred p;\nelect.sync _|p, 0xffffffff;\n@p cp.async.bulk.prefetch.L2.global [%0], %1;\n}" ::"l"(src), "r"(bytes) : "memory");
}
__device__ __forceinline__ uint32_t ld_relaxed(const uint32_t* p) { uint32_t v; asm volatile("ld.relaxed.gpu.global.u32 %0, [%1];" : "=r"(v) : "l"(p) : "memory"); return v; }
__device__ __forceinline__ void st_relaxed(uint32_t* p, uint32_t v) { asm volatile("st.relaxed.gpu.global.u32 [%0], %1;" ::"l"(p), "r"(v) : "memory"); }
__device__ __forceinline__ uint4 ld_relaxed4(const uint4* p) { uint4 v; asm volatile("ld.relaxed.gpu.global.v4.u32 {%0,%1,%2,%3}, [%4];" : "=r"(v.x), "=r"(v.y), "=r"(v.z), "=r"(v.w) : "l"(p) : "memory"); return v; }
__device__ __forceinline__ void st_relaxed4(uint4* p, uint4 v) { asm volatile("st.relaxed.gpu.global.v4.u32 [%0], {%1,%2,%3,%4};" ::"l"(p), "r"(v.x), "r"(v.y), "r"(v.z), "r"(v.w) : "memory"); }
__device__ __forceinline__ uint4 ldg_nc4(const void* p) { uint4 v; asm volatile("ld.global.nc.L1::no_allocate.v4.u32 {%0,%1,%2,%3}, [%4];" : "=r"(v.x), "=r"(v.y), "=r"(v.z), "=r"(v.w) : "l"(p)); return v; }
__device__ __forceinline__ uint32_t ldg_nc(const void* p) { uint32_t v; asm volatile("ld.global.nc.u32 %0, [%1];" : "=r"(v) : "l"(p)); return v; }
__device__ __forceinline__ uint32_t ld_acquire(const uint32_t* p) { uint32_t v; asm volatile("ld.acquire.gpu.global.u32 %0, [%1];" : "=r"(v) : "l"(p) : "memory"); return v; }
__device__ __forceinline__ uint4 lds4(uint32_t a) { uint4 v; asm volatile("ld.shared.v4.u32 {%0,%1,%2,%3}, [%4];" : "=r"(v.x), "=r"(v.y), "=r"(v.z), "=r"(v.w) : "r"(a) : "memory"); return v; }
__device__ __forceinline__ float2 lds2f(uint32_t a) { float2 v; asm volatile("ld.shared.v2.f32 {%0,%1}, [%2];" : "=f"(v.x), "=f"(v.y) : "r"(a) : "memory"); return v; }
__device__ __forceinline__ uint32_t lds1(uint32_t a) { uint32_t v; asm volatile("ld.shared.u32 %0, [%1];" : "=r"(v) : "r"(a) : "memory"); return v; }
__device__ __forceinline__ void sts4(uint32_t a, uint4 v) { asm volatile("st.shared.v4.u32 [%0], {%1,%2,%3,%4};" ::"r"(a), "r"(v.x), "r"(v.y), "r"(v.z), "r"(v.w) : "memory"); }
__device__ __forceinline__ void sts2(uint32_t a, uint32_t x, uint32_t y) { asm volatile("st.shared.v2.u32 [%0], {%1,%2};" ::"r"(a), "r"(x), "r"(y) : "memory"); }
__device__ __forceinline__ void sts1(uint32_t a, uint32_t v) { asm volatile("st.shared.u32 [%0], %1;" ::"r"(a), "r"(v) : "memory"); }
__device__ __forceinline__ void stsm4(uint32_t a, uint32_t r0, uint32_t r1, uint32_t r2, uint32_t r3) {
    asm volatile("stmatrix.sync.aligned.m8n8.x4.shared.b16 [%0], {%1,%2,%3,%4};" ::"r"(a), "r"(r0), "r"(r1), "r"(r2), "r"(r3));
}
__device__ __forceinline__ uint32_t pack2(float lo, float hi) { uint32_t r; asm("cvt.rn.bf16x2.f32 %0, %1, %2;" : "=r"(r) : "f"(hi), "f"(lo)); return r; }
__device__ __forceinline__ uint32_t pack2_relu(float lo, float hi) { uint32_t r; asm("cvt.rn.relu.bf16x2.f32 %0, %1, %2;" : "=r"(r) : "f"(hi), "f"(lo)); return r; }
__device__ __forceinline__ uint32_t hfma2(uint32_t a, uint32_t b, uint32_t c) { uint32_t r; asm("fma.rn.bf16x2 %0, %1, %2, %3;" : "=r"(r) : "r"(a), "r"(b), "r"(c)); return r; }
__device__ __forceinline__ uint32_t hmul2(uint32_t a, uint32_t b) { uint32_t r; asm("mul.rn.bf16x2 %0, %1, %2;" : "=r"(r) : "r"(a), "r"(b)); return r; }
__device__ __forceinline__ float bf_lo(uint32_t v) { return __uint_as_float(v << 16); }
__device__ __forceinline__ float bf_hi(uint32_t v) { return __uint_as_float(v & 0xFFFF0000u); }
__device__ __forceinline__ float bf_round(float v) { return bf_lo(pack2(v, 0.f)); }
__device__ __forceinline__ float ex2(float x) { float r; asm("ex2.approx.ftz.f32 %0, %1;" : "=f"(r) : "f"(x)); return r; }
__device__ __forceinline__ void mma16816(float* d, uint32_t a0, uint32_t a1, uint32_t a2, uint32_t a3, uint32_t b0, uint32_t b1) {
    asm("mma.sync.aligned.m16n8k16.row.col.f32.bf16.bf16.f32 {%0,%1,%2,%3}, {%4,%5,%6,%7}, {%8,%9}, {%0,%1,%2,%3};"
        : "+f"(d[0]), "+f"(d[1]), "+f"(d[2]), "+f"(d[3]) : "r"(a0), "r"(a1), "r"(a2), "r"(a3), "r"(b0), "r"(b1));
}
__device__ __forceinline__ void mma16816_first(float* d, uint32_t a0, uint32_t a1, uint32_t a2, uint32_t a3, uint32_t b0, uint32_t b1) {
    asm volatile("mma.sync.aligned.m16n8k16.row.col.f32.bf16.bf16.f32 {%0,%1,%2,%3}, {%4,%5,%6,%7}, {%8,%9}, {%10,%10,%10,%10};"
        : "=f"(d[0]), "=f"(d[1]), "=f"(d[2]), "=f"(d[3]) : "r"(a0), "r"(a1), "r"(a2), "r"(a3), "r"(b0), "r"(b1), "f"(0.f));
}
__device__ __forceinline__ void mma16816_v(float* d, uint32_t a0, uint32_t a1, uint32_t a2, uint32_t a3, uint32_t b0, uint32_t b1) {
    asm volatile("mma.sync.aligned.m16n8k16.row.col.f32.bf16.bf16.f32 {%0,%1,%2,%3}, {%4,%5,%6,%7}, {%8,%9}, {%0,%1,%2,%3};"
        : "+f"(d[0]), "+f"(d[1]), "+f"(d[2]), "+f"(d[3]) : "r"(a0), "r"(a1), "r"(a2), "r"(a3), "r"(b0), "r"(b1));
}
__device__ __forceinline__ void mma1688(float* d, uint32_t a0, uint32_t a1, uint32_t b0) {
    asm("mma.sync.aligned.m16n8k8.row.col.f32.bf16.bf16.f32 {%0,%1,%2,%3}, {%4,%5}, {%6}, {%0,%1,%2,%3};"
        : "+f"(d[0]), "+f"(d[1]), "+f"(d[2]), "+f"(d[3]) : "r"(a0), "r"(a1), "r"(b0));
}
__device__ __forceinline__ void ldsm4(uint32_t a, uint32_t* r) {
    asm volatile("ldmatrix.sync.aligned.m8n8.x4.shared.b16 {%0,%1,%2,%3}, [%4];" : "=r"(r[0]), "=r"(r[1]), "=r"(r[2]), "=r"(r[3]) : "r"(a));
}
__device__ __forceinline__ void ldsm4t(uint32_t a, uint32_t* r) {
    asm volatile("ldmatrix.sync.aligned.m8n8.x4.trans.shared.b16 {%0,%1,%2,%3}, [%4];" : "=r"(r[0]), "=r"(r[1]), "=r"(r[2]), "=r"(r[3]) : "r"(a));
}
__device__ __forceinline__ float rcp(float x) { float r; asm("rcp.approx.ftz.f32 %0, %1;" : "=f"(r) : "f"(x)); return r; }
__device__ __forceinline__ uint2 ld_relaxed2(const void* p) { uint2 v; asm volatile("ld.relaxed.gpu.global.v2.u32 {%0,%1}, [%2];" : "=r"(v.x), "=r"(v.y) : "l"(p) : "memory"); return v; }
__device__ __forceinline__ void st_relaxed2(void* p, uint32_t x, uint32_t y) { asm volatile("st.relaxed.gpu.global.v2.u32 [%0], {%1,%2};" ::"l"(p), "r"(max(x, 1u)), "r"(max(y, 1u)) : "memory"); }
__host__ __device__ constexpr uint64_t dconst(uint32_t lbo, uint32_t sbo, uint32_t swz) {
    return ((uint64_t)(lbo >> 4) << 16) | ((uint64_t)(sbo >> 4) << 32) | ((uint64_t)swz << 62);
}
__device__ __forceinline__ uint32_t mkdesc(uint32_t addr, uint64_t c) { return (uint32_t)c | ((addr & 0x3FFFF) >> 4); }
#define WG_FENCE() asm volatile("wgmma.fence.sync.aligned;" ::: "memory")
#define WG_COMMIT() asm volatile("wgmma.commit_group.sync.aligned;" ::: "memory")
#define WG_WAIT(n) asm volatile("wgmma.wait_group.sync.aligned %0;" ::"n"(n) : "memory")
template <int N> __device__ __forceinline__ void reg_fence(float* d) {
#pragma unroll
    for (int i = 0; i < N; i++) asm volatile("" : "+f"(d[i])::"memory");
}
template <int N> __device__ __forceinline__ void reg_def(float* d) {
#pragma unroll
    for (int i = 0; i < N; i++) asm volatile("" : "=f"(d[i]));
}
template <int N> __device__ __forceinline__ void reg_def(uint32_t* d) {
#pragma unroll
    for (int i = 0; i < N; i++) asm volatile("" : "=r"(d[i]));
}
__device__ __forceinline__ bool is_unset(uint4 v) { return min(min(v.x, v.y), min(v.z, v.w)) == 0u; }
__device__ __forceinline__ uint4 nz4(uint32_t a, uint32_t b, uint32_t c, uint32_t d) { return make_uint4(max(a, 1u), max(b, 1u), max(c, 1u), max(d, 1u)); }
__device__ __forceinline__ void wait_flags(const uint32_t* p, uint32_t target, uint32_t mask) {
    int n = 0;
    while (~__ballot_sync(~0u, (int)(ld_relaxed(p) - target) >= 0) & mask) { if (++n > SPIN_LIMIT) __trap(); }
    asm volatile("fence.acquire.gpu;" ::: "memory");
}
__device__ __forceinline__ float silu_bf(uint32_t cbits) {
    const float c = __uint_as_float(cbits << 16);
    return bf_round(__fdividef(c, 1.f + fminf(ex2(-1.4426950408889634f * c), 1e30f)));
}
__device__ __forceinline__ void gemv_part(uint32_t wmbuf, int npanel, int wp, int lane) {
    const uint32_t wa = wmbuf + wp * 512 + (8 * (lane >> 4) + (lane & 7)) * 32 + ((lane >> 3) & 1) * 16;
    uint2 B[4];
#pragma unroll
    for (int i = 0; i < 4; i++) { const float2 v = lds2f(wmbuf + 28672 + (wp + 8 * i) * 32 + (lane & 3) * 8); B[i] = make_uint2(__float_as_uint(v.x), __float_as_uint(v.y)); }
#pragma unroll 1
    for (int pn = 0; pn < npanel; pn++) {
        float d[4] = {};
        uint32_t A[16];
#pragma unroll
        for (int i = 0; i < 4; i++) ldsm4t(wa + pn * 14336 + (i < 3 || wp < 4 ? i : 0) * 4096, A + 4 * i);
#pragma unroll
        for (int i = 0; i < 4; i++) mma16816(d, A[4 * i], A[4 * i + 1], A[4 * i + 2], A[4 * i + 3], B[i].x, B[i].y);
        if ((lane & 3) == 0) {
            sts1(wmbuf + 29696 + (wp * 32 + pn * 16 + (lane >> 2)) * 4, __float_as_uint(d[0]));
            sts1(wmbuf + 29696 + (wp * 32 + pn * 16 + 8 + (lane >> 2)) * 4, __float_as_uint(d[2]));
        }
    }
}
__device__ __forceinline__ int pass_f(int fs, int ps) { return 224 * fs + ((fs & 1) ? (ps == 0 ? 96 : ps == 1 ? 32 : 0) : (ps == 0 ? 0 : ps == 1 ? 128 : 192)); }
__device__ __forceinline__ constexpr uint32_t slot_off(int l) { return (l < 3 || l > 6 ? l : l == 6 ? 3 : l + 1) * 16384; }
__device__ __forceinline__ void ln_coeffs(float mean, float msq, uint32_t& r2, uint32_t& n2) {
    const float rs = bf_round(rsqrtf(fmaxf(msq - mean * mean, 0.f) + 1e-5f));
    r2 = pack2(rs, rs);
    n2 = pack2(-mean * rs, -mean * rs);
}

#define LOADW tma3_e(dst, &p.dn, 112 * nq + 48, f, 0, bar); tma3_e(dst + 4096, &p.dn, 112 * nq, f, 0, bar);
template <int sec> __device__ __forceinline__ void ring_loader(const Params& p, uint32_t sb_, int r_, int j_) {
    const uint32_t sb = opaque(sb_);
    const int r = opaque(r_), j = opaque(j_), nq = j >> 1, fs = 4 * (j & 1) + nq;
    const int fa = pass_f(fs, 0), fb = pass_f(fs, 1), fc = pass_f(fs, 2);
#define BAR(i) (sb + M_BAR + 8 * (i))
#define kh (j & 1)
            int sl = 0;
#pragma unroll 1
            for (int s = 0; s < 28; s++) {
                if (s >= 1 && s < 6) mbar_wait(BAR(B_FULL + s - 1), 0);
                const int ps = s < 14 ? 0 : s < 21 ? 1 : 2;
                const uint32_t half = ps < 2 ? 8192 : 4096;
                mbar_wait(BAR(B_EMPTY + sl), (s >= 7 && s < 14) || s >= 21);
                expect_e(BAR(B_FULL + sl), half);
                tma3_e(sb + slot_off(sl) + sec * half, &p.ga + 2 * ps + sec, 0, ps ? 64 * sl : 32 * s, ps == 0 ? fa >> 6 : ps == 1 ? fb >> 6 : fc >> 5, BAR(B_FULL + sl));
                sl = sl == 6 ? 0 : sl + 1;
            }
            if (!sec) PROFH(3);
#pragma unroll 1
            for (int e = 0; e < 4; e++) {
                const uint32_t dst = sb + slot_off(e) + sec * 8192, bar = BAR(B_FULL + e);
                const int f = (e < 2 ? fa + 64 * e : e == 2 ? fb : fc) + 32 * sec;
                mbar_wait(BAR(B_EMPTY + e), 0);
                expect_e(bar, e == 3 && sec ? 0 : 8192);
                if (!(e == 3 && sec)) { LOADW }
            }
            sl = 4;
            int e = 4;
#pragma unroll 1
            for (int grp = 0; grp < 9; grp++) {
                const int ps = grp >= 6 ? 2 : grp >= 3 ? 1 : 0;
                int sidx = grp - 3 * ps;
                if (sec && sidx == 0) { mbar_wait(BAR(B_HRDY + ps), 0); fence_async_global(); }
                sidx += sidx >= nq;
                int f = pass_f(4 * kh + sidx, ps);
#pragma unroll 1
                for (int k = 4 >> ps; k > 0; k--, e++, f += 32) {
                    const uint32_t dst = sb + slot_off(sl), bar = BAR(B_FULL + sl);
                    mbar_wait(BAR(B_EMPTY + sl), e >= 12 && e < 24);
                    if (e < WIN_END && e >= WIN) mbar_wait(BAR(B_FULL + (sl >= WIN ? sl - WIN : sl + 12 - WIN)), e - WIN >= 12);
                    expect_e(bar, 8192);
                    if (!sec) { LOADW }
                    else bulk_e(dst + 8192, g_h2 + (size_t)r * (224 * 512) + f * 64, 8192, bar);
                    sl = sl == 11 ? 0 : sl + 1;
                }
            }
            if (!sec) PROFH(4);
}

__global__ void __cluster_dims__(2, 1, 1) __launch_bounds__(384, 1) fused_block_kernel(const __grid_constant__ Params p) {
    extern __shared__ __align__(1024) unsigned char smem[];
    const uint32_t sb = (uint32_t)__cvta_generic_to_shared(smem);
    const int tid = threadIdx.x, lane = tid & 31, warp = __shfl_sync(~0u, tid >> 5, 0);
    const int m = blockIdx.x >> 1;
    int r, nq;
    {
        int g, i;
        if (m < MAP_S) { g = m < 4 ? 15 : 16; i = m & 3; }
        else if (m < MAP_S + 32) { g = (m - MAP_S) & 7; i = (m - MAP_S) >> 3; }
        else if (m < MAP_S + 60) { i = (m - MAP_S - 32) / 7; g = 8 + (m - MAP_S - 32) - 7 * i; }
        else { g = 16; i = m & 3; }
        r = g; nq = i;
    }
    const int j = opaque(2 * nq + (blockIdx.x & 1)), b = 8 * r + j, fs = 4 * kh + nq;
    const uint32_t sc = r == 16;
    if (lane == 0 && warp < 9 && warp != 6 && warp != 7) {
        const int i0 = warp == 8 ? 0 : 8 + 8 * warp, cnt = warp == 0 || warp == 8 ? 1 : warp < 3 ? 2 : 8;
#pragma unroll
        for (int k = 0; k < 8; k++) if (i0 + k != B_WMFULL) mbar_init(BAR(i0 + k), cnt);
        asm volatile("fence.mbarrier_init.release.cluster;" ::: "memory");
        fence_async_smem();
    }

    if (warp < 8) {
        const int w = warp >> 2, wi = warp & 3;
#define COORDS const int t = fresh_tid() & 127, lane = t & 31, q = lane & 3, lr = lane >> 2, ra = 64 * w + 16 * wi + lr; \
        const uint32_t lx = (lane >> 4) ^ (lane & 7), mrow = (64 * w + 16 * wi + ((lane >> 3) & 1) * 8 + (lane & 7)) * 128; \
        (void)q; (void)lr; (void)ra; (void)lx; (void)mrow;
        const int sid = 2 * (j & 3) + w;
#define RUN(k) (!sc || sid == (k))
#define WAIT(i, par) mbar_wait_c(BAR(i), (par) | sc)
        constexpr uint64_t DB128 = dconst(4096, 1024, 1);
        bar_arrive(9, 384);
        bar_sync(0, 384);
        asm volatile("barrier.cluster.arrive.relaxed.aligned;" ::: "memory");
        asm volatile("setmaxnreg.inc.sync.aligned.u32 224;");
        PROFC(0);
        uint32_t xr[16];
        {
            COORDS
            uint32_t h[112];
            if (RUN(0)) {
                float ds[4] = {}, da[2][4] = {}, db[2][4] = {};
                const uint32_t ONE2 = 0x3F803F80u;
                if (kh == 0) { WAIT(B_WMFULL, 0); gemv_part(sb + OFF_Y + HALF, 1, warp, lane); warp_arrive(BAR(B_GEMV)); }
#pragma unroll
                for (int kb = 0; kb < 7; kb++) {
                    WAIT(B_XFULL + kb, 0);
#pragma unroll
                    for (int k4 = 0; k4 < 4; k4++) ldsm4(sb + OFF_X + mrow + kb * 16384 + (((2 * k4) ^ lx) << 4), h + 16 * kb + 4 * k4);
#pragma unroll
                    for (int k4 = 0; k4 < 4; k4++) {
                        const uint32_t* f = h + 16 * kb + 4 * k4;
                        mma16816(ds, f[0], f[1], f[2], f[3], ONE2, ONE2);
                        mma1688(da[0], f[0], f[1], f[0]); mma1688(db[0], f[0], f[1], f[1]);
                        mma1688(da[1], f[2], f[3], f[2]); mma1688(db[1], f[2], f[3], f[3]);
                    }
                }
#pragma unroll
                for (int i = 0; i < 4; i++) {
                    const int ch = 7 * j + 2 * i + (lane >> 4);
                    ldsm4(sb + OFF_X + mrow + (ch >> 3) * 16384 + (((ch ^ lane) & 7) << 4), xr + 4 * i);
                }
                warp_arrive(BAR(B_XFREE));
                float qa = (lr & 1) ? da[0][1] + da[1][1] : da[0][0] + da[1][0];
                float qb = (lr & 1) ? db[0][3] + db[1][3] : db[0][2] + db[1][2];
                const int src = (lane & ~3) | (lr >> 1);
                qa = __shfl_sync(~0u, qa, src);
                qb = __shfl_sync(~0u, qb, src);
                uint32_t ra2, na2, rb2, nb2;
                ln_coeffs(ds[0] * (1.f / DM), qa * (1.f / DM), ra2, na2);
                ln_coeffs(ds[2] * (1.f / DM), qb * (1.f / DM), rb2, nb2);
#pragma unroll
                for (int i = 0; i < 112; i += 2) { h[i] = hfma2(h[i], ra2, na2); h[i + 1] = hfma2(h[i + 1], rb2, nb2); }
                if (kh == 1) { WAIT(B_WMFULL, 0); gemv_part(sb + OFF_Y + HALF, 2, warp, lane); warp_arrive(BAR(B_GEMV)); }
            } else { reg_def<112>(h); reg_def<16>(xr); }
            PROFC(1);
            if (RUN(1)) {
                float ak[28], av[28], aq[28];
                uint32_t kp[14], vp[14];
                const uint32_t bk0 = mkdesc(sb + OFF_Y, DB128) + kh, bv0 = mkdesc(sb + OFF_Y + HALF, DB128) + kh, bq0 = mkdesc(sb + OFF_X, DB128) + kh;
                uint32_t* kvg = g_kv + (size_t)(b * 2) * 3584 + (8 * w + 2 * wi) * 224 + lane;
                WAIT(B_FULLK, 0);
                WAIT(B_MOD1, 0);
                PROFC(2);
                reg_def<28>(ak);
#pragma unroll
                for (int g4 = 0; g4 < 4; g4++) {
#pragma unroll
                    for (int ks = 7 * g4; ks < 7 * g4 + 7; ks++) {
                        const uint4 st = *(const uint4*)(smem + M_ST + ks * 64 + q * 16);
                        h[4 * ks] = hfma2(h[4 * ks], st.x, st.y); h[4 * ks + 1] = hfma2(h[4 * ks + 1], st.x, st.y);
                        h[4 * ks + 2] = hfma2(h[4 * ks + 2], st.z, st.w); h[4 * ks + 3] = hfma2(h[4 * ks + 3], st.z, st.w);
                    }
                    WG_FENCE();
#pragma unroll
                    for (int ks = 7 * g4; ks < 7 * g4 + 7; ks++) wgmma_rs_56<DB128>(ak, h[4 * ks], h[4 * ks + 1], h[4 * ks + 2], h[4 * ks + 3], bk0 + ks * 128, ks != 0);
                }
                WG_COMMIT();
                PROFC(3);
                WAIT(B_FULLV, 0);
                reg_def<28>(av);
                WG_FENCE();
#pragma unroll
                for (int ks = 0; ks < 8; ks++) wgmma_rs_56<DB128>(av, h[4 * ks], h[4 * ks + 1], h[4 * ks + 2], h[4 * ks + 3], bv0 + ks * 128, ks != 0);
                WG_COMMIT();
                WG_WAIT(1);
                reg_fence<28>(ak);
#pragma unroll
                for (int g = 0; g < 7; g++) {
                    kp[2 * g] = pack2(ak[4 * g], ak[4 * g + 1]); kp[2 * g + 1] = pack2(ak[4 * g + 2], ak[4 * g + 3]);
                    kvg[g * 32] = kp[2 * g]; kvg[224 + g * 32] = kp[2 * g + 1];
                }
                warp_arrive(BAR(B_PUB));
                PROFC(4);
                WG_FENCE();
#pragma unroll
                for (int ks = 8; ks < 28; ks++) wgmma_rs_56<DB128>(av, h[4 * ks], h[4 * ks + 1], h[4 * ks + 2], h[4 * ks + 3], bv0 + ks * 128, 1);
                WG_COMMIT();
                WAIT(B_FULLQ, 0);
                reg_def<28>(aq);
                WG_FENCE();
#pragma unroll
                for (int ks = 0; ks < 8; ks++) wgmma_rs_56<DB128>(aq, h[4 * ks], h[4 * ks + 1], h[4 * ks + 2], h[4 * ks + 3], bq0 + ks * 128, ks != 0);
                WG_COMMIT();
                WG_WAIT(1);
                reg_fence<28>(av);
#pragma unroll
                for (int g = 0; g < 7; g++) {
                    vp[2 * g] = pack2(av[4 * g], av[4 * g + 1]); vp[2 * g + 1] = pack2(av[4 * g + 2], av[4 * g + 3]);
                    kvg[3584 + g * 32] = vp[2 * g]; kvg[3584 + 224 + g * 32] = vp[2 * g + 1];
                }
                warp_arrive(BAR(B_PUB + 1));
                PROFC(5);
                WG_FENCE();
#pragma unroll
                for (int ks = 8; ks < 28; ks++) wgmma_rs_56<DB128>(aq, h[4 * ks], h[4 * ks + 1], h[4 * ks + 2], h[4 * ks + 3], bq0 + ks * 128, 1);
                WG_COMMIT();
                WAIT(B_PUB + 1, 0);
                const uint32_t ko = sb + OFF_Y + Y_KOWN + (8 * w + 2 * wi) * 896 + lane * 4;
                const uint32_t qo = sb + OFF_Y + Y_Q + (8 * w + 2 * wi) * 1024 + lane * 4;
#pragma unroll
                for (int g = 0; g < 7; g++) {
                    sts1(ko + g * 128, kp[2 * g]); sts1(ko + 896 + g * 128, kp[2 * g + 1]);
                    sts1(ko + (Y_VOWN - Y_KOWN) + g * 128, vp[2 * g]); sts1(ko + (Y_VOWN - Y_KOWN) + 896 + g * 128, vp[2 * g + 1]);
                }
                WG_WAIT(0);
                reg_fence<28>(aq);
                __syncwarp();
                if (lane < 3 && w == 1) mbar_arrive(BAR(B_EMPTY + lane));
#pragma unroll
                for (int g = 0; g < 7; g++) {
                    const uint32_t q0 = pack2(aq[4 * g], aq[4 * g + 1]), q1 = pack2(aq[4 * g + 2], aq[4 * g + 3]);
                    if (g == 3) {
                        sts1(qo + 3 * 128, q < 2 ? q0 : 0u); sts1(qo + 1024 + 3 * 128, q < 2 ? q1 : 0u);
                        sts1(qo + 4 * 128, q < 2 ? 0u : q0); sts1(qo + 1024 + 4 * 128, q < 2 ? 0u : q1);
                    } else {
                        const int ch = g < 3 ? g : g + 1;
                        sts1(qo + ch * 128, q0); sts1(qo + 1024 + ch * 128, q1);
                    }
                }
                if (!sc) bar_sync(3, 256);
            }
        }
        PROFC(6);
        WAIT(B_KRFULL, 0);
        PROFC(7);
        if (RUN(2)) {
#pragma unroll 1
            for (int hf = sc; hf < 2; hf++) {
                COORDS
                float s[136];
                float na = 0.f, nb = 0.f;
                const float CS = 0.18898223650461361f * 1.4426950408889634f;
                const int kg0 = 8 * hf + 2 * wi;
                const int pmin = 16 - 8 * r - 4 * hf - wi;
                const float NEG = __int_as_float(0xFF800000);
                {
                    uint32_t F[8];
                    const uint32_t qa = sb + OFF_Y + Y_Q + (kg0 + ((lane >> 3) & 1)) * 1024 + (4 * w + (lane >> 4)) * 128 + (lane & 7) * 16;
                    ldsm4(qa, F); ldsm4(qa + 256, F + 4);
                    uint32_t ka = sb + OFF_Y + Y_K + kg0 * 896 + (3 * w + (lane >> 3)) * 128 + (lane & 7) * 16;
#pragma unroll
                    for (int g = 0; g < 34; g++) {
                        uint32_t B[4];
                        if (g >= 12 && g % 4 == 0) ka += __float_as_uint(s[4 * (g - 12)]) & p.zero;
                        ldsm4(ka + g * 896, B);
                        mma16816_first(s + 4 * g, F[0], F[1], F[2], F[3], B[0], B[1]);
                        mma16816_v(s + 4 * g, F[4], F[5], F[6], F[7], B[2], B[3]);
                    }
                    const bool c0 = 2 * q > lr, c1 = 2 * q + 1 > lr;
                    if (!c0) { s[0] = NEG; s[6] = NEG; }
                    if (!c1) { s[1] = NEG; s[7] = NEG; }
                    s[2] = NEG; s[3] = NEG;
                    if (c0) { s[128] = NEG; s[134] = NEG; }
                    if (c1) { s[129] = NEG; s[135] = NEG; }
                    s[132] = NEG; s[133] = NEG;
                    float ma = NEG, mb = NEG;
#pragma unroll
                    for (int pp = 0; pp < 17; pp++) {
                        const float* e = s + 8 * pp;
                        const float bias = pp < pmin ? NEG : 0.f;
                        ma = fmaxf(ma, fmaxf(fmaxf(e[0], e[1]), fmaxf(e[4], e[5])) + bias);
                        mb = fmaxf(mb, fmaxf(fmaxf(e[2], e[3]), fmaxf(e[6], e[7])) + bias);
                    }
                    ma = fmaxf(ma, __shfl_xor_sync(~0u, ma, 1)); mb = fmaxf(mb, __shfl_xor_sync(~0u, mb, 1));
                    ma = fmaxf(ma, __shfl_xor_sync(~0u, ma, 2)); mb = fmaxf(mb, __shfl_xor_sync(~0u, mb, 2));
                    na = -ma * CS; nb = -mb * CS;
                }
                PROFC(8 + 3 * hf);
                {
                    WAIT(B_VRFULL, 0);
                    float o[16] = {}, rs[4] = {};
                    uint32_t pk[2];
                    const uint32_t va = sb + OFF_Y + Y_VR + (kg0 + ((lane >> 3) & 1)) * 896 + (3 * w + (lane >> 4)) * 128 + (lane & 7) * 16;
#pragma unroll
                    for (int pp = 0; pp < 17; pp++) {
                        uint32_t B[8];
                        const uint32_t v = va + pp * 1792 + (pp == 16 || (pp >= 9 && kg0 + 2 * pp >= 32) ? Y_VOWN - 32 * 896 : 0);
                        ldsm4t(v, B); ldsm4t(v + 256, B + 4);
                        float e[8];
                        const float bias = __uint_as_float((pp < pmin ? 0xFF800000u : 0u) | ((pp < 2 ? B[0] : pk[pp & 1]) & p.zero));
#pragma unroll
                        for (int i = 0; i < 8; i++) e[i] = ex2(fmaf(s[8 * pp + i], CS, ((i & 2) ? nb : na) + bias));
                        const uint32_t p0 = pack2(e[0], e[1]), p1 = pack2(e[2], e[3]), p2 = pack2(e[4], e[5]), p3 = pack2(e[6], e[7]);
                        pk[pp & 1] = p3;
                        mma16816(rs, p0, p1, p2, p3, 0x3F803F80u, 0x3F803F80u);
#pragma unroll
                        for (int g = 0; g < 4; g++) mma16816(o + 4 * g, p0, p1, p2, p3, B[2 * g], B[2 * g + 1]);
                    }
                    PROFC(9 + 3 * hf);
                    const float ia = rcp(rs[0]), ib = rcp(rs[2]);
                    uint32_t* og = g_o + (size_t)(2 * r + hf) * 14336 + (7 * j + 3 * w) * 256 + wi * 64 + lane;
#pragma unroll
                    for (int g = 0; g < 4; g++) {
                        if ((g == 3 - 3 * w) ? ((q >> 1) == w) : true) {
                            og[g * 256] = pack2(o[4 * g] * ia, o[4 * g + 1] * ia);
                            og[g * 256 + 32] = pack2(o[4 * g + 2] * ib, o[4 * g + 3] * ib);
                        }
                    }
                    warp_arrive(BAR(B_PUB + 2 + hf));
                    PROFC(10 + 3 * hf);
                }
            }
        }
        uint32_t x1p[14];
        COORDS
        constexpr uint64_t DT = dconst(1024, 128, 0);
        if (RUN(4)) {
            float ac[28];
            const uint32_t ad = mkdesc(sb + (w ? OFF_Y + HALF : OFF_X), DT), bd = mkdesc(sb + OFF_X + HALF, DB128) + kh;
            WAIT(B_WOFULL, 0);
            WAIT(B_MOD2, 0);
            WAIT(B_GFULL + w, 0);
            PROFC(28);
            reg_def<28>(ac);
#pragma unroll 1
            for (int u = 0; u < 4; u++) {
                WG_FENCE();
#pragma unroll
                for (int i = 0; i < 7; i++) wgmma_ss_56<DT, DB128>(ac, ad + (7 * u + i) * 128, bd + (7 * u + i) * 128, (u | i) != 0);
            }
            WG_COMMIT();
            WG_WAIT(0);
            reg_fence<28>(ac);
            PROFC(14);
            __syncwarp();
            if (lane < 3) mbar_arrive(BAR(B_EMPTY + 3 + lane));
            if (lane < 3 && w == 0) mbar_arrive(BAR(B_EMPTY + lane));
            float s1a = 0.f, s2a = 0.f, s1b = 0.f, s2b = 0.f;
            uint32_t* xo = g_x1 + (size_t)(2 * r + w) * 14336 + 7 * j * 256 + wi * 64 + lane;
#pragma unroll
            for (int g = 0; g < 7; g++) {
                const float2 ga = *(const float2*)(smem + M_G + (8 * g + 2 * q) * 4);
                x1p[2 * g] = pack2(fmaf(ga.x, ac[4 * g], bf_lo(xr[2 * g])), fmaf(ga.y, ac[4 * g + 1], bf_hi(xr[2 * g])));
                x1p[2 * g + 1] = pack2(fmaf(ga.x, ac[4 * g + 2], bf_lo(xr[2 * g + 1])), fmaf(ga.y, ac[4 * g + 3], bf_hi(xr[2 * g + 1])));
                xo[g * 256] = x1p[2 * g]; xo[g * 256 + 32] = x1p[2 * g + 1];
                const float u0 = bf_lo(x1p[2 * g]), u1 = bf_hi(x1p[2 * g]), u2 = bf_lo(x1p[2 * g + 1]), u3 = bf_hi(x1p[2 * g + 1]);
                s1a += u0 + u1; s2a += u0 * u0 + u1 * u1; s1b += u2 + u3; s2b += u2 * u2 + u3 * u3;
            }
            float ka = (q & 1) ? s2a : s1a, kb2 = (q & 1) ? s2b : s1b;
            ka += __shfl_xor_sync(~0u, (q & 1) ? s1a : s2a, 1); kb2 += __shfl_xor_sync(~0u, (q & 1) ? s1b : s2b, 1);
            const float kk = ((q & 2) ? kb2 : ka) + __shfl_xor_sync(~0u, (q & 2) ? ka : kb2, 2);
            ((float*)g_st)[(((2 * r + w) * 8 + j) * 64 + 16 * wi + lr + 4 * (q & 2)) * 2 + (q & 1)] = kk;
            __syncwarp();
            if (lane < 2) mbar_arrive(BAR(B_PUB + 4 + w));
        } else reg_def<14>(x1p);
        PROFC(15);
        uint32_t h2a[32], h2b[24];
        if (RUN(6)) {
            const int fa = pass_f(fs, 0), fb = pass_f(fs, 1), fc = pass_f(fs, 2);
            uint32_t* h2g = g_h2 + (size_t)r * (224 * 512) + (8 * w + 2 * wi) * 32 + lane;
            const uint32_t a0 = mkdesc(sb + OFF_Y + w * HALF, DT);
            {
                WAIT(B_GFULL + 2 + w, 0);
                PROFC(16);
                float2 sa = make_float2(0.f, 0.f), sbb = sa;
#pragma unroll
                for (int jj = 0; jj < 8; jj++) {
                    const float2 u = lds2f(sb + OFF_X + X_STAT + w * 4096 + (jj * 64 + 16 * wi + lr) * 8), v = lds2f(sb + OFF_X + X_STAT + w * 4096 + (jj * 64 + 16 * wi + lr + 8) * 8);
                    sa.x += u.x; sa.y += u.y; sbb.x += v.x; sbb.y += v.y;
                }
                warp_arrive(BAR(B_EMPTY + 6));
                uint32_t ra2, na2, rb2, nb2;
                ln_coeffs(sa.x * (1.f / DM), sa.y * (1.f / DM), ra2, na2);
                ln_coeffs(sbb.x * (1.f / DM), sbb.y * (1.f / DM), rb2, nb2);
                const uint32_t ha = sb + OFF_Y + w * HALF + (lane >> 4) * 1024 + (2 * wi + ((lane >> 3) & 1)) * 128 + (lane & 7) * 16;
                const uint32_t sta = sb + M_ST + q * 16;
                auto prep = [&](int s, uint32_t* f) {
                    uint32_t x[8];
                    ldsm4(ha + s * 4096, x); ldsm4(ha + s * 4096 + 2048, x + 4);
                    const uint4 st[2] = {lds4(sta + s * 128), lds4(sta + s * 128 + 64)};
#pragma unroll
                    for (int i = 0; i < 2; i++) {
                        f[4 * i] = hfma2(hfma2(x[4 * i], ra2, na2), st[i].x, st[i].y); f[4 * i + 1] = hfma2(hfma2(x[4 * i + 1], rb2, nb2), st[i].x, st[i].y);
                        f[4 * i + 2] = hfma2(hfma2(x[4 * i + 2], ra2, na2), st[i].z, st[i].w); f[4 * i + 3] = hfma2(hfma2(x[4 * i + 3], rb2, nb2), st[i].z, st[i].w);
                    }
                    stsm4(ha + s * 4096, f[0], f[1], f[2], f[3]); stsm4(ha + s * 4096 + 2048, f[4], f[5], f[6], f[7]);
                };
                float ac[128];
                uint32_t fr[3][8];
                const uint32_t bx = mkdesc(sb, DB128);
                reg_def<128>(ac);
                prep(0, fr[0]);
                PROFC(17);
#pragma unroll
                for (int s = 0; s < 14; s++) {
                    const uint32_t* f = fr[s % 3];
                    const uint32_t bd = bx + (slot_off(s % 7) >> 4);
                    WAIT(B_FULL + s % 7, s >= 7);
                    WG_FENCE();
                    wgmma_rs_256<DB128>(ac, f[0], f[1], f[2], f[3], bd, s != 0);
                    wgmma_rs_256<DB128>(ac, f[4], f[5], f[6], f[7], bd + 128, 1);
                    WG_COMMIT();
                    if (s < 13) prep(s + 1, fr[(s + 1) % 3]);
                    if (s > 0) { WG_WAIT(1); warp_arrive(BAR(B_EMPTY + (s - 1) % 7)); }
                }
                PROFC(18);
                fence_async_smem();
                WG_WAIT(0);
                reg_fence<128>(ac);
                warp_arrive(BAR(B_EMPTY + 6));
#pragma unroll
                for (int g = 0; g < 16; g++) {
                    h2a[2 * g] = hmul2(pack2_relu(ac[4 * g], ac[4 * g + 1]), pack2(ac[64 + 4 * g], ac[64 + 4 * g + 1]));
                    h2a[2 * g + 1] = hmul2(pack2_relu(ac[4 * g + 2], ac[4 * g + 3]), pack2(ac[64 + 4 * g + 2], ac[64 + 4 * g + 3]));
                    h2g[(fa / 8 + g) * 512] = h2a[2 * g]; h2g[(fa / 8 + g) * 512 + 32] = h2a[2 * g + 1];
                }
                warp_arrive(BAR(B_PUB + 6));
                bar_sync(1 + w, 128);
            }
            PROFC(19);
            {
                float ac[64];
                reg_def<64>(ac);
                const uint32_t bx = mkdesc(sb, dconst(8192, 1024, 1));
#pragma unroll kB
                for (int s = 0; s < 7; s++) {
                    WAIT(B_FULL + s, 0);
                    const uint32_t ad = a0 + s * 512, bd = bx + (slot_off(s) >> 4);
                    WG_FENCE();
#pragma unroll
                    for (int k = 0; k < 4; k++) wgmma_ss_128<DT, DB128>(ac, ad + k * 128, bd + k * 128, (s | k) != 0);
                    WG_COMMIT();
                    if (s > 0) { WG_WAIT(1); warp_arrive(BAR(B_EMPTY + s - 1)); }
                }
                WG_WAIT(0);
                reg_fence<64>(ac);
                warp_arrive(BAR(B_EMPTY + 6));
#pragma unroll
                for (int g = 0; g < 8; g++) {
                    h2b[2 * g] = hmul2(pack2_relu(ac[4 * g], ac[4 * g + 1]), pack2(ac[32 + 4 * g], ac[32 + 4 * g + 1]));
                    h2b[2 * g + 1] = hmul2(pack2_relu(ac[4 * g + 2], ac[4 * g + 3]), pack2(ac[32 + 4 * g + 2], ac[32 + 4 * g + 3]));
                    h2g[(fb / 8 + g) * 512] = h2b[2 * g]; h2g[(fb / 8 + g) * 512 + 32] = h2b[2 * g + 1];
                }
                warp_arrive(BAR(B_PUB + 7));
            }
            PROFC(27);
            {
                float ac[32];
                reg_def<32>(ac);
                const uint32_t bx = mkdesc(sb, dconst(4096, 512, 2));
#pragma unroll kC
                for (int s = 0; s < 7; s++) {
                    WAIT(B_FULL + s, 1);
                    const uint32_t ad = a0 + p.zero + s * 512, bd = bx + (slot_off(s) >> 4);
                    WG_FENCE();
#pragma unroll
                    for (int k = 0; k < 4; k++) wgmma_ss_64<DT, dconst(4096, 512, 2)>(ac, ad + k * 128, bd + k * 64, (s | k) != 0);
                    WG_COMMIT();
                    if (s > 0) { WG_WAIT(1); warp_arrive(BAR(B_EMPTY + s - 1)); }
                }
                WG_WAIT(0);
                reg_fence<32>(ac);
                __syncwarp();
                if (lane < 6) mbar_arrive(BAR(B_EMPTY + 6 + lane));
                PROFC(20);
#pragma unroll
                for (int g = 0; g < 4; g++) {
                    h2b[16 + 2 * g] = hmul2(pack2_relu(ac[4 * g], ac[4 * g + 1]), pack2(ac[16 + 4 * g], ac[16 + 4 * g + 1]));
                    h2b[16 + 2 * g + 1] = hmul2(pack2_relu(ac[4 * g + 2], ac[4 * g + 3]), pack2(ac[16 + 4 * g + 2], ac[16 + 4 * g + 3]));
                    h2g[(fc / 8 + g) * 512] = h2b[16 + 2 * g]; h2g[(fc / 8 + g) * 512 + 32] = h2b[16 + 2 * g + 1];
                }
                warp_arrive(BAR(B_PUB + 8));
                asm volatile("barrier.cluster.wait.aligned;" ::: "memory");
                if (lane == 0 && !sc) {
                    uint32_t rb;
                    asm volatile("mapa.shared::cluster.u32 %0, %1, %2;" : "=r"(rb) : "r"(BAR(B_PEER)), "r"(kh ^ 1));
                    asm volatile("mbarrier.arrive.relaxed.cluster.shared::cluster.b64 _, [%0];" ::"r"(rb) : "memory");
                }
            }
        } else { reg_def<32>(h2a); reg_def<24>(h2b); }
        PROFC(21);
        if (RUN(7)) {
            float ac[56];
            reg_def<56>(ac);
            constexpr uint64_t DAN = dconst(2048, 128, 0);
            const uint32_t bx = mkdesc(sb, DB128);
#pragma unroll
            for (int e = 0; e < 4; e++) {
                WAIT(B_FULL + e, 0);
                const uint32_t bd = bx + (slot_off(e) >> 4);
                const uint32_t* hh = e < 2 ? h2a + 16 * e : h2b + 16 * (e - 2);
                WG_FENCE();
#pragma unroll
                for (int k = 0; k < (e < 3 ? 4 : 2); k++) wgmma_rs_112<DB128>(ac, hh[4 * k], hh[4 * k + 1], hh[4 * k + 2], hh[4 * k + 3], bd + (k >> 1) * 512 + (k & 1) * 128, (e | k) != 0);
                WG_COMMIT();
                if (e > 0) { WG_WAIT(1); warp_arrive(BAR(B_EMPTY + e - 1)); }
            }
            PROFC(22);
            const uint32_t ax = mkdesc(sb + 8192 + w * 1024, DAN);
#pragma unroll kG2
            for (int e = 4; e < 25; e++) {
                WAIT(B_FULL + e % 12, e >= 12 && e < 24);
                if (e == 16) PROFC(23);
                const uint32_t z = (e / 12) * p.zero;
                const uint32_t ad = ax + z + (slot_off(e % 12) >> 4), bd = bx + z + (slot_off(e % 12) >> 4);
                WG_FENCE();
                wgmma_ss_112<DAN, DB128>(ac, ad, bd, 1);
                wgmma_ss_112<DAN, DB128>(ac, ad + 256, bd + 128, 1);
                WG_COMMIT();
                if (e < 14) { WG_WAIT(1); warp_arrive(BAR(B_EMPTY + (e - 1) % 12)); }
            }
            mbar_wait_cluster(BAR(B_PEER), sc);
            WG_WAIT(0);
            reg_fence<56>(ac);
            PROFC(24);
            uint32_t rdst, rbar;
            asm volatile("mapa.shared::cluster.u32 %0, %1, %2;" : "=r"(rdst) : "r"(sb + OFF_Y + (5 + w) * 16384 + t * 16), "r"(kh ^ 1 ^ sc));
            asm volatile("mapa.shared::cluster.u32 %0, %1, %2;" : "=r"(rbar) : "r"(BAR(B_XCH + w)), "r"(kh ^ 1 ^ sc));
#define ACG(g, i) ac[4 * (((g) + 8) % 14) + (i)]
#pragma unroll
            for (int g = 0; g < 7; g++) {
                const float v0 = kh ? ACG(g, 0) : ACG(g + 7, 0), v1 = kh ? ACG(g, 1) : ACG(g + 7, 1);
                const float v2 = kh ? ACG(g, 2) : ACG(g + 7, 2), v3 = kh ? ACG(g, 3) : ACG(g + 7, 3);
                if (!sc) asm volatile("st.async.shared::cluster.mbarrier::complete_tx::bytes.v4.f32 [%0], {%1,%2,%3,%4}, [%5];"
                             ::"r"(rdst + g * 2048), "f"(v0), "f"(v1), "f"(v2), "f"(v3), "r"(rbar) : "memory");
            }
            mbar_wait_cluster(BAR(B_XCH + w), sc);
            PROFC(25);
            bf16* og = (sc ? (bf16*)(g_h2 + 16 * 224 * 512) : p.out + (size_t)128 * r * DM) + (size_t)ra * DM + 56 * j + 2 * q;
#pragma unroll
            for (int g = 0; g < 7; g++) {
                const uint4 rv = *(const uint4*)(smem + OFF_Y + (5 + w) * 16384 + t * 16 + g * 2048);
                const float2 gb = *(const float2*)(smem + M_G + 224 + (8 * g + 2 * q) * 4);
                const float v0 = (kh ? ACG(g + 7, 0) : ACG(g, 0)) + __uint_as_float(rv.x), v1 = (kh ? ACG(g + 7, 1) : ACG(g, 1)) + __uint_as_float(rv.y);
                const float v2 = (kh ? ACG(g + 7, 2) : ACG(g, 2)) + __uint_as_float(rv.z), v3 = (kh ? ACG(g + 7, 3) : ACG(g, 3)) + __uint_as_float(rv.w);
                *(uint32_t*)(og + 8 * g) = pack2(fmaf(gb.x, v0, bf_lo(x1p[2 * g])), fmaf(gb.y, v1, bf_hi(x1p[2 * g])));
                *(uint32_t*)(og + 8 * DM + 8 * g) = pack2(fmaf(gb.x, v2, bf_lo(x1p[2 * g + 1])), fmaf(gb.y, v3, bf_hi(x1p[2 * g + 1])));
            }
        }
        PROFC(26);
        bar_sync(1 + w, 128);
        if (wi == 0) warp_arrive(BAR(B_DONE));
    } else {
        const int lane = fresh_tid() & 31;
        const bool early = kh == 0, gemv = r < 14;
        const int mcol = early ? 16 * (4 * r + nq) : 2 * DM + 32 * (4 * r + nq);
        const uint32_t wmbuf = sb + OFF_Y + HALF;
        asm volatile("setmaxnreg.dec.sync.aligned.u32 56;");
        if (warp == 9) {
#pragma unroll
            for (int i = 56; i < 64; i++) init_e(BAR(i), 1);
            fence_async_smem();
        }
        if (warp == 8) { init_e(BAR(B_WMFULL), 2); fence_async_smem(); }
        bar_arrive(0, 384);
        asm volatile("barrier.cluster.arrive.relaxed.aligned;" ::: "memory");
        uint32_t target = 0;
        if (warp == 8) {
            if (!sc) {
                expect_e(BAR(B_WMFULL), gemv ? 28672 >> early : 0);
                if (early && gemv) { tma3_e(wmbuf, &p.wm, mcol, 0, 0, BAR(B_WMFULL)); tma3_e(wmbuf + 7168, &p.wm, mcol, 224, 0, BAR(B_WMFULL)); }
#pragma unroll 1
                for (int kb = 0; kb < 7; kb++) {
                    expect_e(BAR(B_XFULL + kb), 16384);
                    tma3_e(sb + OFF_X + kb * 16384, &p.xm, 64 * kb, 128 * r, 0, BAR(B_XFULL + kb));
                }
            }
#pragma unroll 1
            for (int mt = 0; mt < 4; mt++) {
                if (mt == 1) {
                    if (!early && gemv) {
#pragma unroll 1
                        for (int k = 0; k < 4; k++) tma3_e(wmbuf + k * 7168, &p.wm, mcol + (k >> 1) * 16, (k & 1) * 224, 0, BAR(B_WMFULL));
                    }
                    bar_sync(9, 384);
                    if (sc) return;
                    mbar_wait(BAR(B_MOD1), 0);
                    mbar_wait(BAR(B_WMFREE), 0);
                }
                if (mt == 2) mbar_wait(BAR(B_XFREE), 0);
                if (mt == 3) mbar_wait(BAR(B_VRFULL), 0);
                const uint32_t bar = BAR(mt == 3 ? B_WOFULL : B_FULLK + mt), dst = sb + (mt < 2 ? OFF_Y : OFF_X) + (mt & 1) * HALF;
                const int c0 = (mt < 2 ? DM + DM * mt : 0) + 56 * j - 8 * kh;
                if (!sc) {
                    expect_e(bar, HALF);
                    tma3_e(dst, mt == 3 ? &p.wo : &p.qkv, c0, 0, 0, bar);
                    tma3_e(dst + HALF / 2, mt == 3 ? &p.wo : &p.qkv, c0, 224, 0, bar);
                }
            }
            expect_e(BAR(B_XCH), 14336);
            expect_e(BAR(B_XCH + 1), 14336);
        } else {
            if (warp == 10 && !sc) {
                l2_prefetch_e((const char*)p.wqkv + (size_t)b * 9408, 9408);
                if (lane == 0) sts1(sb + M_EPOCH, atomicAdd(&g_ticket, 1u) / NCTA);
            }
            if (warp == 11) {
#pragma unroll
                for (int i = 0; i < 8; i++) {
                    const int wd = lane + 32 * i;
                    const uint32_t cb = i < 7 ? __ldg((const uint32_t*)p.c + wd) : 0u;
                    sts1(wmbuf + 28672 + (wd >> 3) * 32 + (wd & 3) * 8 + (wd & 4), pack2(silu_bf(cb & 0xFFFFu), silu_bf(cb >> 16)));
                }
            }
            bar_sync(9, 384);
            if (sc) return;
            target = lds1(sb + M_EPOCH) + 1;
            const uint32_t tag = target & 0xFFFFu;
            if (warp == 11) {
                warp_arrive(BAR(B_WMFULL));
                mbar_wait(BAR(B_GEMV), 0);
                float sum = 0.f;
#pragma unroll
                for (int i = 0; i < 8; i++) sum += *(const float*)(smem + OFF_Y + HALF + 29696 + (i * 32 + (early ? lane & 15 : lane)) * 4);
                const uint32_t word = (pack2(sum, 0.f) << 16) | tag;
                if (gemv) {
                    uint32_t* mg = g_mod + mcol + (early ? (lane & 15) + (lane >> 4) * 4 * 6 * DM : lane);
#pragma unroll
                    for (int i = 0; i < 8; i++) if (i < 4 || !early) st_relaxed(mg + i * 6 * DM, word);
                }
                warp_arrive(BAR(B_WMFREE));
            }
            const uint4* modp = (const uint4*)g_mod + (r & 7) * (6 * DM / 4);
            const bool p2 = warp == 11;
            mbar_wait(BAR(p2 ? B_PUB : B_XFULL + 4), 0);
#pragma unroll 1
            for (int it = p2 ? 0 : warp - 9; it < (p2 ? 2 : warp - 8); it++) {
                const int i0 = lane + 32 * it, imax = p2 ? 251 : 223;
                uint4 v[4];
#pragma unroll 1
                for (int n = 0;; n++) {
                    uint32_t bad = 0;
#pragma unroll
                    for (int k = 0; k < 4; k++) {
                        const int i = min(i0 + 64 * k, imax);
                        v[k] = ld_relaxed4(modp + (i < 224 ? (p2 ? 336 : 0) + i : (i < 238 ? 14 * j + i : 14 * j + i + 322)));
                        bad |= (v[k].x ^ tag) | (v[k].y ^ tag) | (v[k].z ^ tag) | (v[k].w ^ tag);
                    }
                    if (!__any_sync(~0u, bad & 0xFFFFu)) break;
                    if (n > SPIN_LIMIT) __trap();
                }
#pragma unroll
                for (int k = 0; k < 4; k++) {
                    const int i = min(i0 + 64 * k, imax);
                    if (i < 224) {
                        const int isc = i >= 112, c4 = i - 112 * isc;
                        const float one = isc ? 1.f : 0.f;
                        const uint32_t a = sb + M_ST + (c4 >> 2) * 64 + (c4 & 1) * 32 + (c4 & 2) * 4 + (isc ? 0 : 4);
                        sts1(a, pack2(bf_hi(v[k].x) + one, bf_hi(v[k].y) + one));
                        sts1(a + 16, pack2(bf_hi(v[k].z) + one, bf_hi(v[k].w) + one));
                    } else {
                        sts4(sb + M_G + (i - 224) * 16, make_uint4(v[k].x & 0xFFFF0000u, v[k].y & 0xFFFF0000u, v[k].z & 0xFFFF0000u, v[k].w & 0xFFFF0000u));
                    }
                }
                warp_arrive(BAR(p2 ? B_MOD2 : B_MOD1));
            }
            if (warp == 9) {
#pragma unroll 1
                for (int kv = 0; kv < 2; kv++) {
                    mbar_wait(BAR(B_PUB + kv), 0);
                    wait_flags(g_flag + b * 96 + lane, target, (r >= 2 ? 6u : r == 1 ? 2u : 0u) << (8 * kv));
                    fence_async_global();
                    const uint32_t dst = sb + OFF_Y + (kv ? Y_VR : Y_K);
                    expect_e(BAR(B_KRFULL + kv), r >= 2 ? 28672 : r == 1 ? 14336 : 0);
                    if (r >= 2) bulk_e(dst, g_kv + (size_t)((b - 16) * 2 + kv) * 3584, 14336, BAR(B_KRFULL + kv));
                    if (r >= 1) bulk_e(dst + 14336, g_kv + (size_t)((b - 8) * 2 + kv) * 3584, 14336, BAR(B_KRFULL + kv));
                }
            } else if (warp == 11) {
                mbar_wait(BAR(B_VRFULL), 0);
                l2_prefetch_e((const char*)p.wg + (size_t)b * 12544, 12544);
                l2_prefetch_e((const char*)p.wu + (size_t)b * 12544, 12544);
                l2_prefetch_e((const char*)p.wd + (size_t)b * 12544, 12544);
            }
        }
        if (warp == 8 || warp == 11) {
            const int sec = warp == 11;
            if (sec) ring_loader<1>(p, sb, r, j); else ring_loader<0>(p, sb, r, j);
            mbar_wait(BAR(B_DONE), 0);
        } else if (warp == 9) {
#pragma unroll
            for (int ev = 0; ev < 4; ev++) expect_e(BAR(B_GFULL + ev), ev < 2 ? HALF : HALF + 4096);
            mbar_wait(BAR(B_PUB + 2), 0);
            const uint32_t* fp = g_flag + b * 96 + 32 + lane;
            const uint32_t* src = g_ox + (size_t)2 * r * 14336;
            const float2* ssrc = g_st + 2 * r * 512;
#pragma unroll 1
            for (int n = 0, ev = 0; ev < 4; n++) {
                if (ev == 1) mbar_wait(BAR(B_PUB + 3), 0);
                uint32_t ok = __ballot_sync(~0u, (int)(ld_relaxed(fp) - target) >= 0) >> (8 * ev);
                while ((ok & 0xFFu) == 0xFFu) {
                    asm volatile("fence.acquire.gpu;" ::: "memory");
                    fence_async_global();
                    const uint32_t bar = BAR(B_GFULL + ev);
                    bulk_e(sb + (ev == 0 ? OFF_X : OFF_Y + (ev & 1) * HALF), src + (ev >> 1) * (34 * 14336) + (ev & 1) * 14336, HALF, bar);
                    if (ev >= 2) bulk_e(sb + OFF_X + X_STAT + (ev & 1) * 4096, ssrc + (ev & 1) * 512, 4096, bar);
                    if (ev) PROFH(4 + ev);
                    ev++; ok >>= 8;
                }
                if (n > SPIN_LIMIT) __trap();
            }
#pragma unroll 1
            for (int ps = 0; ps < 3; ps++) {
                mbar_wait(BAR(B_PUB + 6 + ps), 0);
                wait_flags(g_flag + b * 96 + 64 + lane, target, (0x55u << kh) << (8 * ps));
                warp_arrive(BAR(B_HRDY + ps));
                PROFH(9 + ps);
            }
        } else {
#pragma unroll 1
            for (int k = 0; k < 9; k++) {
                uint32_t* fp = k < 2 ? g_flag + (b + 8 * lane) * 96 + k * 8 + lane : g_flag + (8 * r + lane) * 96 + 16 + k * 8 + j;
                mbar_wait(BAR(B_PUB + k), 0);
                fence_gpu();
                if (k < 2 ? (lane == 1 || lane == 2) : lane < 8) st_relaxed(fp, target);
                if (k >= 3 && k <= 5) PROFH(k - 3);
            }
        }
    }
}

typedef CUresult (*EncodeFn)(CUtensorMap*, CUtensorMapDataType, cuuint32_t, void*, const cuuint64_t*, const cuuint64_t*, const cuuint32_t*,
                             const cuuint32_t*, CUtensorMapInterleave, CUtensorMapSwizzle, CUtensorMapL2promotion, CUtensorMapFloatOOBfill);

static void make_map(EncodeFn fn, CUtensorMap* m, const void* ptr, uint64_t d0, uint64_t d1, uint64_t d2, uint64_t s1, uint64_t s2,
                     uint32_t b0, uint32_t b1, uint32_t b2, CUtensorMapSwizzle sw) {
    cuuint64_t dims[3] = {d0, d1, d2}, strides[2] = {s1, s2};
    cuuint32_t box[3] = {b0, b1, b2}, es[3] = {1, 1, 1};
    CUresult rc = fn(m, CU_TENSOR_MAP_DATA_TYPE_BFLOAT16, 3, (void*)ptr, dims, strides, box, es, CU_TENSOR_MAP_INTERLEAVE_NONE, sw,
                     CU_TENSOR_MAP_L2_PROMOTION_L2_128B, CU_TENSOR_MAP_FLOAT_OOB_FILL_NONE);
    (void)rc;
}

extern "C" void kernel_launch(void* const* d_in, const int* in_sizes, int n_in, void* d_out, int out_size) {
    (void)in_sizes; (void)n_in; (void)out_size;
    static EncodeFn fn = nullptr;
    if (!fn) {
        cudaDriverEntryPointQueryResult st;
        cudaGetDriverEntryPoint("cuTensorMapEncodeTiled", (void**)&fn, cudaEnableDefault, &st);
        cudaFuncSetAttribute(fused_block_kernel, cudaFuncAttributeMaxDynamicSharedMemorySize, SMEM_BYTES);
    }
    Params p;
    p.x = (const bf16*)d_in[0];
    const bf16* wqkv = (const bf16*)d_in[1];
    p.wqkv = wqkv;
    p.wop = (const bf16*)d_in[2];
    p.wg = (const bf16*)d_in[4];
    p.wu = (const bf16*)d_in[5];
    p.wd = (const bf16*)d_in[6];
    p.c = (const bf16*)d_in[7];
    p.wmod = (const bf16*)d_in[8];
    p.out = (bf16*)d_out;
    p.zero = 0;
    make_map(fn, &p.wm, p.wmod, 2688, 448, 1, 5376, 5376 * 448, 16, 224, 1, CU_TENSOR_MAP_SWIZZLE_NONE);
    make_map(fn, &p.xm, p.x, 448, 2048, 1, 896, 896 * 2048, 64, 128, 1, CU_TENSOR_MAP_SWIZZLE_128B);
    make_map(fn, &p.qkv, wqkv, 1344, 448, 1, 2688, 2688 * 448, 64, 224, 1, CU_TENSOR_MAP_SWIZZLE_128B);
    make_map(fn, &p.wo, p.wop, 448, 448, 1, 896, 896 * 448, 64, 224, 1, CU_TENSOR_MAP_SWIZZLE_128B);
    make_map(fn, &p.ga, p.wg, 64, 448, 28, 3584, 128, 64, 32, 2, CU_TENSOR_MAP_SWIZZLE_128B);
    make_map(fn, &p.ua, p.wu, 64, 448, 28, 3584, 128, 64, 32, 2, CU_TENSOR_MAP_SWIZZLE_128B);
    make_map(fn, &p.gb, p.wg, 64, 448, 28, 3584, 128, 64, 64, 1, CU_TENSOR_MAP_SWIZZLE_128B);
    make_map(fn, &p.ub, p.wu, 64, 448, 28, 3584, 128, 64, 64, 1, CU_TENSOR_MAP_SWIZZLE_128B);
    make_map(fn, &p.gc, p.wg, 32, 448, 56, 3584, 64, 32, 64, 1, CU_TENSOR_MAP_SWIZZLE_64B);
    make_map(fn, &p.uc, p.wu, 32, 448, 56, 3584, 64, 32, 64, 1, CU_TENSOR_MAP_SWIZZLE_64B);
    make_map(fn, &p.dn, p.wd, 448, 1792, 1, 896, 896 * 1792, 64, 32, 1, CU_TENSOR_MAP_SWIZZLE_128B);
    fused_block_kernel<<<GRID, 384, SMEM_BYTES>>>(p);
}
```

```cpp
#include <cuda_runtime.h>
#include <cuda_bf16.h>
#include <cuda.h>
#include <stdint.h>

typedef __nv_bfloat16 bf16;

template<uint64_t CB> __device__ __forceinline__ void wgmma_rs_56(float* d, uint32_t a0, uint32_t a1, uint32_t a2, uint32_t a3, uint32_t db, int sd) {
  asm volatile("{\n.reg .pred p;\n.reg .b64 b;\nsetp.ne.b32 p, %33, 0;\nmov.b64 b, {%32, %34};\n"
    "wgmma.mma_async.sync.aligned.m64n56k16.f32.bf16.bf16 {%0,%1,%2,%3,%4,%5,%6,%7,%8,%9,%10,%11,%12,%13,%14,%15,%16,%17,%18,%19,%20,%21,%22,%23,%24,%25,%26,%27}, {%28,%29,%30,%31}, b, p, 1, 1, 1;\n}\n"
    : "+f"(d[0]),"+f"(d[1]),"+f"(d[2]),"+f"(d[3]),"+f"(d[4]),"+f"(d[5]),"+f"(d[6]),"+f"(d[7]),"+f"(d[8]),"+f"(d[9]),"+f"(d[10]),"+f"(d[11]),"+f"(d[12]),"+f"(d[13]),"+f"(d[14]),"+f"(d[15]),"+f"(d[16]),"+f"(d[17]),"+f"(d[18]),"+f"(d[19]),"+f"(d[20]),"+f"(d[21]),"+f"(d[22]),"+f"(d[23]),"+f"(d[24]),"+f"(d[25]),"+f"(d[26]),"+f"(d[27])
    : "r"(a0), "r"(a1), "r"(a2), "r"(a3), "r"(db), "r"(sd), "n"((uint32_t)(CB >> 32)));
}
template<uint64_t CA, uint64_t CB> __device__ __forceinline__ void wgmma_ss_56(float* d, uint32_t da, uint32_t db, int sd) {
  asm volatile("{\n.reg .pred p;\n.reg .b64 a, b;\nsetp.ne.b32 p, %30, 0;\nmov.b64 a, {%28, %31};\nmov.b64 b, {%29, %32};\n"
    "wgmma.mma_async.sync.aligned.m64n56k16.f32.bf16.bf16 {%0,%1,%2,%3,%4,%5,%6,%7,%8,%9,%10,%11,%12,%13,%14,%15,%16,%17,%18,%19,%20,%21,%22,%23,%24,%25,%26,%27}, a, b, p, 1, 1, 0, 1;\n}\n"
    : "+f"(d[0]),"+f"(d[1]),"+f"(d[2]),"+f"(d[3]),"+f"(d[4]),"+f"(d[5]),"+f"(d[6]),"+f"(d[7]),"+f"(d[8]),"+f"(d[9]),"+f"(d[10]),"+f"(d[11]),"+f"(d[12]),"+f"(d[13]),"+f"(d[14]),"+f"(d[15]),"+f"(d[16]),"+f"(d[17]),"+f"(d[18]),"+f"(d[19]),"+f"(d[20]),"+f"(d[21]),"+f"(d[22]),"+f"(d[23]),"+f"(d[24]),"+f"(d[25]),"+f"(d[26]),"+f"(d[27])
    : "r"(da), "r"(db), "r"(sd), "n"((uint32_t)(CA >> 32)), "n"((uint32_t)(CB >> 32)));
}
template<uint64_t CB> __device__ __forceinline__ void wgmma_rs_256(float* d, uint32_t a0, uint32_t a1, uint32_t a2, uint32_t a3, uint32_t db, int sd) {
  asm volatile("{\n.reg .pred p;\n.reg .b64 b;\nsetp.ne.b32 p, %133, 0;\nmov.b64 b, {%132, %134};\n"
    "wgmma.mma_async.sync.aligned.m64n256k16.f32.bf16.bf16 {%0,%1,%2,%3,%4,%5,%6,%7,%8,%9,%10,%11,%12,%13,%14,%15,%16,%17,%18,%19,%20,%21,%22,%23,%24,%25,%26,%27,%28,%29,%30,%31,%32,%33,%34,%35,%36,%37,%38,%39,%40,%41,%42,%43,%44,%45,%46,%47,%48,%49,%50,%51,%52,%53,%54,%55,%56,%57,%58,%59,%60,%61,%62,%63,%64,%65,%66,%67,%68,%69,%70,%71,%72,%73,%74,%75,%76,%77,%78,%79,%80,%81,%82,%83,%84,%85,%86,%87,%88,%89,%90,%91,%92,%93,%94,%95,%96,%97,%98,%99,%100,%101,%102,%103,%104,%105,%106,%107,%108,%109,%110,%111,%112,%113,%114,%115,%116,%117,%118,%119,%120,%121,%122,%123,%124,%125,%126,%127}, {%128,%129,%130,%131}, b, p, 1, 1, 1;\n}\n"
    : "+f"(d[0]),"+f"(d[1]),"+f"(d[2]),"+f"(d[3]),"+f"(d[4]),"+f"(d[5]),"+f"(d[6]),"+f"(d[7]),"+f"(d[8]),"+f"(d[9]),"+f"(d[10]),"+f"(d[11]),"+f"(d[12]),"+f"(d[13]),"+f"(d[14]),"+f"(d[15]),"+f"(d[16]),"+f"(d[17]),"+f"(d[18]),"+f"(d[19]),"+f"(d[20]),"+f"(d[21]),"+f"(d[22]),"+f"(d[23]),"+f"(d[24]),"+f"(d[25]),"+f"(d[26]),"+f"(d[27]),"+f"(d[28]),"+f"(d[29]),"+f"(d[30]),"+f"(d[31]),"+f"(d[32]),"+f"(d[33]),"+f"(d[34]),"+f"(d[35]),"+f"(d[36]),"+f"(d[37]),"+f"(d[38]),"+f"(d[39]),"+f"(d[40]),"+f"(d[41]),"+f"(d[42]),"+f"(d[43]),"+f"(d[44]),"+f"(d[45]),"+f"(d[46]),"+f"(d[47]),"+f"(d[48]),"+f"(d[49]),"+f"(d[50]),"+f"(d[51]),"+f"(d[52]),"+f"(d[53]),"+f"(d[54]),"+f"(d[55]),"+f"(d[56]),"+f"(d[57]),"+f"(d[58]),"+f"(d[59]),"+f"(d[60]),"+f"(d[61]),"+f"(d[62]),"+f"(d[63]),"+f"(d[64]),"+f"(d[65]),"+f"(d[66]),"+f"(d[67]),"+f"(d[68]),"+f"(d[69]),"+f"(d[70]),"+f"(d[71]),"+f"(d[72]),"+f"(d[73]),"+f"(d[74]),"+f"(d[75]),"+f"(d[76]),"+f"(d[77]),"+f"(d[78]),"+f"(d[79]),"+f"(d[80]),"+f"(d[81]),"+f"(d[82]),"+f"(d[83]),"+f"(d[84]),"+f"(d[85]),"+f"(d[86]),"+f"(d[87]),"+f"(d[88]),"+f"(d[89]),"+f"(d[90]),"+f"(d[91]),"+f"(d[92]),"+f"(d[93]),"+f"(d[94]),"+f"(d[95]),"+f"(d[96]),"+f"(d[97]),"+f"(d[98]),"+f"(d[99]),"+f"(d[100]),"+f"(d[101]),"+f"(d[102]),"+f"(d[103]),"+f"(d[104]),"+f"(d[105]),"+f"(d[106]),"+f"(d[107]),"+f"(d[108]),"+f"(d[109]),"+f"(d[110]),"+f"(d[111]),"+f"(d[112]),"+f"(d[113]),"+f"(d[114]),"+f"(d[115]),"+f"(d[116]),"+f"(d[117]),"+f"(d[118]),"+f"(d[119]),"+f"(d[120]),"+f"(d[121]),"+f"(d[122]),"+f"(d[123]),"+f"(d[124]),"+f"(d[125]),"+f"(d[126]),"+f"(d[127])
    : "r"(a0), "r"(a1), "r"(a2), "r"(a3), "r"(db), "r"(sd), "n"((uint32_t)(CB >> 32)));
}
template<uint64_t CA, uint64_t CB> __device__ __forceinline__ void wgmma_ss_128(float* d, uint32_t da, uint32_t db, int sd) {
  asm volatile("{\n.reg .pred p;\n.reg .b64 a, b;\nsetp.ne.b32 p, %66, 0;\nmov.b64 a, {%64, %67};\nmov.b64 b, {%65, %68};\n"
    "wgmma.mma_async.sync.aligned.m64n128k16.f32.bf16.bf16 {%0,%1,%2,%3,%4,%5,%6,%7,%8,%9,%10,%11,%12,%13,%14,%15,%16,%17,%18,%19,%20,%21,%22,%23,%24,%25,%26,%27,%28,%29,%30,%31,%32,%33,%34,%35,%36,%37,%38,%39,%40,%41,%42,%43,%44,%45,%46,%47,%48,%49,%50,%51,%52,%53,%54,%55,%56,%57,%58,%59,%60,%61,%62,%63}, a, b, p, 1, 1, 0, 1;\n}\n"
    : "+f"(d[0]),"+f"(d[1]),"+f"(d[2]),"+f"(d[3]),"+f"(d[4]),"+f"(d[5]),"+f"(d[6]),"+f"(d[7]),"+f"(d[8]),"+f"(d[9]),"+f"(d[10]),"+f"(d[11]),"+f"(d[12]),"+f"(d[13]),"+f"(d[14]),"+f"(d[15]),"+f"(d[16]),"+f"(d[17]),"+f"(d[18]),"+f"(d[19]),"+f"(d[20]),"+f"(d[21]),"+f"(d[22]),"+f"(d[23]),"+f"(d[24]),"+f"(d[25]),"+f"(d[26]),"+f"(d[27]),"+f"(d[28]),"+f"(d[29]),"+f"(d[30]),"+f"(d[31]),"+f"(d[32]),"+f"(d[33]),"+f"(d[34]),"+f"(d[35]),"+f"(d[36]),"+f"(d[37]),"+f"(d[38]),"+f"(d[39]),"+f"(d[40]),"+f"(d[41]),"+f"(d[42]),"+f"(d[43]),"+f"(d[44]),"+f"(d[45]),"+f"(d[46]),"+f"(d[47]),"+f"(d[48]),"+f"(d[49]),"+f"(d[50]),"+f"(d[51]),"+f"(d[52]),"+f"(d[53]),"+f"(d[54]),"+f"(d[55]),"+f"(d[56]),"+f"(d[57]),"+f"(d[58]),"+f"(d[59]),"+f"(d[60]),"+f"(d[61]),"+f"(d[62]),"+f"(d[63])
    : "r"(da), "r"(db), "r"(sd), "n"((uint32_t)(CA >> 32)), "n"((uint32_t)(CB >> 32)));
}
template<uint64_t CA, uint64_t CB> __device__ __forceinline__ void wgmma_ss_64(float* d, uint32_t da, uint32_t db, int sd) {
  asm volatile("{\n.reg .pred p;\n.reg .b64 a, b;\nsetp.ne.b32 p, %34, 0;\nmov.b64 a, {%32, %35};\nmov.b64 b, {%33, %36};\n"
    "wgmma.mma_async.sync.aligned.m64n64k16.f32.bf16.bf16 {%0,%1,%2,%3,%4,%5,%6,%7,%8,%9,%10,%11,%12,%13,%14,%15,%16,%17,%18,%19,%20,%21,%22,%23,%24,%25,%26,%27,%28,%29,%30,%31}, a, b, p, 1, 1, 0, 1;\n}\n"
    : "+f"(d[0]),"+f"(d[1]),"+f"(d[2]),"+f"(d[3]),"+f"(d[4]),"+f"(d[5]),"+f"(d[6]),"+f"(d[7]),"+f"(d[8]),"+f"(d[9]),"+f"(d[10]),"+f"(d[11]),"+f"(d[12]),"+f"(d[13]),"+f"(d[14]),"+f"(d[15]),"+f"(d[16]),"+f"(d[17]),"+f"(d[18]),"+f"(d[19]),"+f"(d[20]),"+f"(d[21]),"+f"(d[22]),"+f"(d[23]),"+f"(d[24]),"+f"(d[25]),"+f"(d[26]),"+f"(d[27]),"+f"(d[28]),"+f"(d[29]),"+f"(d[30]),"+f"(d[31])
    : "r"(da), "r"(db), "r"(sd), "n"((uint32_t)(CA >> 32)), "n"((uint32_t)(CB >> 32)));
}
template<uint64_t CA, uint64_t CB> __device__ __forceinline__ void wgmma_ss_112(float* d, uint32_t da, uint32_t db, int sd) {
  asm volatile("{\n.reg .pred p;\n.reg .b64 a, b;\nsetp.ne.b32 p, %58, 0;\nmov.b64 a, {%56, %59};\nmov.b64 b, {%57, %60};\n"
    "wgmma.mma_async.sync.aligned.m64n112k16.f32.bf16.bf16 {%0,%1,%2,%3,%4,%5,%6,%7,%8,%9,%10,%11,%12,%13,%14,%15,%16,%17,%18,%19,%20,%21,%22,%23,%24,%25,%26,%27,%28,%29,%30,%31,%32,%33,%34,%35,%36,%37,%38,%39,%40,%41,%42,%43,%44,%45,%46,%47,%48,%49,%50,%51,%52,%53,%54,%55}, a, b, p, 1, 1, 0, 1;\n}\n"
    : "+f"(d[0]),"+f"(d[1]),"+f"(d[2]),"+f"(d[3]),"+f"(d[4]),"+f"(d[5]),"+f"(d[6]),"+f"(d[7]),"+f"(d[8]),"+f"(d[9]),"+f"(d[10]),"+f"(d[11]),"+f"(d[12]),"+f"(d[13]),"+f"(d[14]),"+f"(d[15]),"+f"(d[16]),"+f"(d[17]),"+f"(d[18]),"+f"(d[19]),"+f"(d[20]),"+f"(d[21]),"+f"(d[22]),"+f"(d[23]),"+f"(d[24]),"+f"(d[25]),"+f"(d[26]),"+f"(d[27]),"+f"(d[28]),"+f"(d[29]),"+f"(d[30]),"+f"(d[31]),"+f"(d[32]),"+f"(d[33]),"+f"(d[34]),"+f"(d[35]),"+f"(d[36]),"+f"(d[37]),"+f"(d[38]),"+f"(d[39]),"+f"(d[40]),"+f"(d[41]),"+f"(d[42]),"+f"(d[43]),"+f"(d[44]),"+f"(d[45]),"+f"(d[46]),"+f"(d[47]),"+f"(d[48]),"+f"(d[49]),"+f"(d[50]),"+f"(d[51]),"+f"(d[52]),"+f"(d[53]),"+f"(d[54]),"+f"(d[55])
    : "r"(da), "r"(db), "r"(sd), "n"((uint32_t)(CA >> 32)), "n"((uint32_t)(CB >> 32)));
}
template<uint64_t CB> __device__ __forceinline__ void wgmma_rs_112(float* d, uint32_t a0, uint32_t a1, uint32_t a2, uint32_t a3, uint32_t db, int sd) {
  asm volatile("{\n.reg .pred p;\n.reg .b64 b;\nsetp.ne.b32 p, %61, 0;\nmov.b64 b, {%60, %62};\n"
    "wgmma.mma_async.sync.aligned.m64n112k16.f32.bf16.bf16 {%0,%1,%2,%3,%4,%5,%6,%7,%8,%9,%10,%11,%12,%13,%14,%15,%16,%17,%18,%19,%20,%21,%22,%23,%24,%25,%26,%27,%28,%29,%30,%31,%32,%33,%34,%35,%36,%37,%38,%39,%40,%41,%42,%43,%44,%45,%46,%47,%48,%49,%50,%51,%52,%53,%54,%55}, {%56,%57,%58,%59}, b, p, 1, 1, 1;\n}\n"
    : "+f"(d[0]),"+f"(d[1]),"+f"(d[2]),"+f"(d[3]),"+f"(d[4]),"+f"(d[5]),"+f"(d[6]),"+f"(d[7]),"+f"(d[8]),"+f"(d[9]),"+f"(d[10]),"+f"(d[11]),"+f"(d[12]),"+f"(d[13]),"+f"(d[14]),"+f"(d[15]),"+f"(d[16]),"+f"(d[17]),"+f"(d[18]),"+f"(d[19]),"+f"(d[20]),"+f"(d[21]),"+f"(d[22]),"+f"(d[23]),"+f"(d[24]),"+f"(d[25]),"+f"(d[26]),"+f"(d[27]),"+f"(d[28]),"+f"(d[29]),"+f"(d[30]),"+f"(d[31]),"+f"(d[32]),"+f"(d[33]),"+f"(d[34]),"+f"(d[35]),"+f"(d[36]),"+f"(d[37]),"+f"(d[38]),"+f"(d[39]),"+f"(d[40]),"+f"(d[41]),"+f"(d[42]),"+f"(d[43]),"+f"(d[44]),"+f"(d[45]),"+f"(d[46]),"+f"(d[47]),"+f"(d[48]),"+f"(d[49]),"+f"(d[50]),"+f"(d[51]),"+f"(d[52]),"+f"(d[53]),"+f"(d[54]),"+f"(d[55])
    : "r"(a0), "r"(a1), "r"(a2), "r"(a3), "r"(db), "r"(sd), "n"((uint32_t)(CB >> 32)));
}

constexpr int DM = 448;
constexpr int NCTA = 128;
#define MAPPING 1
#define GRID 132
#define PINGPONG 0
#define WIN 6
#define WIN_END 25
#define UNR_G2 21
#define UNR_B 7
#define UNR_C 7
constexpr int kG2 = UNR_G2, kB = UNR_B, kC = UNR_C;
#define MAP_S 4
constexpr int SPIN_LIMIT = 1 << 22;

constexpr uint32_t OFF_X = 0, OFF_Y = 114688, OFF_MISC = 229376, SMEM_BYTES = 232448;
constexpr uint32_t Y_VR = 0, Y_K = 28672, Y_KOWN = 57344, Y_VOWN = 71680, Y_Q = 86016;
constexpr uint32_t HALF = 57344;
constexpr uint32_t M_BAR = OFF_MISC;
constexpr uint32_t M_ST = OFF_MISC + 512;
constexpr uint32_t M_G = OFF_MISC + 2304;
constexpr uint32_t M_EPOCH = OFF_MISC + 3040;
enum { B_XFULL = 0, B_FULLK = 7, B_FULLV = 8, B_FULLQ, B_KRFULL, B_VRFULL, B_WOFULL, B_XCH, B_FULL = 16, B_MOD1 = 28, B_MOD2, B_WMFULL,
       B_EMPTY = 32, B_XFREE = B_EMPTY + 12, B_GEMV, B_PEER,
       B_PUB = 47,
       B_WMFREE = 56, B_HRDY, B_GFULL = B_HRDY + 3, B_DONE = 31 };
constexpr uint32_t X_STAT = 49152;

__device__ uint32_t g_ticket;
__device__ __align__(128) uint32_t g_mod[8 * 6 * DM];
__device__ __align__(128) uint32_t g_flag[144 * 128];
__device__ __align__(128) uint32_t g_kv[17 * 8 * 2 * 3584];
__device__ __align__(128) uint32_t g_ox[2 * 34 * 14336];
#define g_o g_ox
#define g_x1 (g_ox + 34 * 14336)
__device__ __align__(128) float2 g_st[34 * 8 * 64];
__device__ __align__(128) uint32_t g_wd[56 * 4 * 1792];
__device__ __align__(128) uint32_t g_h2[17 * 224 * 512];
#define PROFH(id)
#define PROFH1(id)
#define PROFC(id)

struct alignas(64) Params {
    CUtensorMap wm, xm, qkv, wo, ga, ua, gb, ub, gc, uc, dn;
    const bf16 *x, *c, *wqkv, *wmod, *wg, *wu, *wd, *wop;
    bf16* out;
    uint32_t zero;
};

__device__ __forceinline__ void mbar_init(uint32_t bar, int cnt) { asm volatile("mbarrier.init.shared::cta.b64 [%0], %1;" ::"r"(bar), "r"(cnt) : "memory"); }
__device__ __forceinline__ void mbar_expect_tx(uint32_t bar, uint32_t bytes) { asm volatile("mbarrier.arrive.expect_tx.shared::cta.b64 _, [%0], %1;" ::"r"(bar), "r"(bytes) : "memory"); }
__device__ __forceinline__ void mbar_arrive(uint32_t bar) { asm volatile("mbarrier.arrive.shared::cta.b64 _, [%0];" ::"r"(bar) : "memory"); }
__device__ __forceinline__ void mbar_wait(uint32_t bar, uint32_t parity) {
    uint32_t ok; int n = 0;
    do {
        asm volatile("{\n.reg .pred p;\nmbarrier.try_wait.parity.shared::cta.b64 p, [%1], %2;\nselp.u32 %0, 1, 0, p;\n}" : "=r"(ok) : "r"(bar), "r"(parity) : "memory");
        if (++n > SPIN_LIMIT) __trap();
    } while (!ok);
}
__device__ __forceinline__ void mbar_wait_c(uint32_t bar, uint32_t parity) {
    asm volatile("{\n.reg .pred p;\nWL:\nmbarrier.try_wait.parity.shared::cta.b64 p, [%0], %1;\n@!p bra WL;\n}" ::"r"(bar), "r"(parity) : "memory");
}
__device__ __forceinline__ void mbar_wait_cluster(uint32_t bar, uint32_t parity) {
    uint32_t ok; int n = 0;
    do {
        asm volatile("{\n.reg .pred p;\nmbarrier.try_wait.parity.acquire.cluster.shared::cta.b64 p, [%1], %2;\nselp.u32 %0, 1, 0, p;\n}" : "=r"(ok) : "r"(bar), "r"(parity) : "memory");
        if (++n > SPIN_LIMIT) __trap();
    } while (!ok);
}
__device__ __forceinline__ void warp_arrive(uint32_t bar) {
    __syncwarp();
    asm volatile("{\n.reg .pred p;\nelect.sync _|p, 0xffffffff;\n@p mbarrier.arrive.shared::cta.b64 _, [%0];\n}" ::"r"(bar) : "memory");
}
__device__ __forceinline__ int opaque(int v) { return __shfl_sync(~0u, v, 0); }
__device__ __forceinline__ int fresh_tid() { int v; asm volatile("mov.u32 %0, %%tid.x;" : "=r"(v)); return v; }
__device__ __forceinline__ void bar_sync(int id, int n) { asm volatile("bar.sync %0, %1;" ::"r"(id), "r"(n) : "memory"); }
__device__ __forceinline__ void bar_arrive(int id, int n) { asm volatile("bar.arrive %0, %1;" ::"r"(id), "r"(n) : "memory"); }
__device__ __forceinline__ void fence_async_smem() { asm volatile("fence.proxy.async.shared::cta;" ::: "memory"); }
__device__ __forceinline__ void fence_async_global() { asm volatile("fence.proxy.async.global;" ::: "memory"); }
__device__ __forceinline__ void fence_gpu() { asm volatile("fence.release.gpu;" ::: "memory"); }
__device__ __forceinline__ void tma3(uint32_t dst, const CUtensorMap* m, int c0, int c1, int c2, uint32_t bar) {
    asm volatile("cp.async.bulk.tensor.3d.shared::cluster.global.mbarrier::complete_tx::bytes [%0], [%1, {%3, %4, %5}], [%2];"
                 ::"r"(dst), "l"(m), "r"(bar), "r"(c0), "r"(c1), "r"(c2) : "memory");
}
__device__ __forceinline__ void bulk_load(uint32_t dst, const void* src, uint32_t bytes, uint32_t bar) {
    asm volatile("cp.async.bulk.shared::cluster.global.mbarrier::complete_tx::bytes [%0], [%1], %2, [%3];" ::"r"(dst), "l"(src), "r"(bytes), "r"(bar) : "memory");
}
__device__ __forceinline__ void expect_e(uint32_t bar, uint32_t bytes) {
    asm volatile("{\n.reg .pred p;\nelect.sync _|p, 0xffffffff;\n@p mbarrier.arrive.expect_tx.shared::cta.b64 _, [%0], %1;\n}" ::"r"(bar), "r"(bytes) : "memory");
}
__device__ __forceinline__ void tma3_e(uint32_t dst, const CUtensorMap* m, int c0, int c1, int c2, uint32_t bar) {
    asm volatile("{\n.reg .pred p;\nelect.sync _|p, 0xffffffff;\n@p cp.async.bulk.tensor.3d.shared::cluster.global.mbarrier::complete_tx::bytes [%0], [%1, {%3, %4, %5}], [%2];\n}"
                 ::"r"(dst), "l"(m), "r"(bar), "r"(c0), "r"(c1), "r"(c2) : "memory");
}
__device__ __forceinline__ void bulk_e(uint32_t dst, const void* src, uint32_t bytes, uint32_t bar) {
    asm volatile("{\n.reg .pred p;\nelect.sync _|p, 0xffffffff;\n@p cp.async.bulk.shared::cluster.global.mbarrier::complete_tx::bytes [%0], [%1], %2, [%3];\n}"
                 ::"r"(dst), "l"(src), "r"(bytes), "r"(bar) : "memory");
}
__device__ __forceinline__ void init_e(uint32_t bar, int cnt) {
    asm volatile("{\n.reg .pred p;\nelect.sync _|p, 0xffffffff;\n@p mbarrier.init.shared::cta.b64 [%0], %1;\n}" ::"r"(bar), "r"(cnt) : "memory");
}
__device__ __forceinline__ void l2_prefetch_e(const void* src, uint32_t bytes) {
    asm volatile("{\n.reg .pred p;\nelect.sync _|p, 0xffffffff;\n@p cp.async.bulk.prefetch.L2.global [%0], %1;\n}" ::"l"(src), "r"(bytes) : "memory");
}
__device__ __forceinline__ uint32_t ld_relaxed(const uint32_t* p) { uint32_t v; asm volatile("ld.relaxed.gpu.global.u32 %0, [%1];" : "=r"(v) : "l"(p) : "memory"); return v; }
__device__ __forceinline__ void st_relaxed(uint32_t* p, uint32_t v) { asm volatile("st.relaxed.gpu.global.u32 [%0], %1;" ::"l"(p), "r"(v) : "memory"); }
__device__ __forceinline__ uint4 ld_relaxed4(const uint4* p) { uint4 v; asm volatile("ld.relaxed.gpu.global.v4.u32 {%0,%1,%2,%3}, [%4];" : "=r"(v.x), "=r"(v.y), "=r"(v.z), "=r"(v.w) : "l"(p) : "memory"); return v; }
__device__ __forceinline__ void st_relaxed4(uint4* p, uint4 v) { asm volatile("st.relaxed.gpu.global.v4.u32 [%0], {%1,%2,%3,%4};" ::"l"(p), "r"(v.x), "r"(v.y), "r"(v.z), "r"(v.w) : "memory"); }
__device__ __forceinline__ uint4 ldg_nc4(const void* p) { uint4 v; asm volatile("ld.global.nc.L1::no_allocate.v4.u32 {%0,%1,%2,%3}, [%4];" : "=r"(v.x), "=r"(v.y), "=r"(v.z), "=r"(v.w) : "l"(p)); return v; }
__device__ __forceinline__ uint32_t ldg_nc(const void* p) { uint32_t v; asm volatile("ld.global.nc.u32 %0, [%1];" : "=r"(v) : "l"(p)); return v; }
__device__ __forceinline__ uint32_t ld_acquire(const uint32_t* p) { uint32_t v; asm volatile("ld.acquire.gpu.global.u32 %0, [%1];" : "=r"(v) : "l"(p) : "memory"); return v; }
__device__ __forceinline__ uint4 lds4(uint32_t a) { uint4 v; asm volatile("ld.shared.v4.u32 {%0,%1,%2,%3}, [%4];" : "=r"(v.x), "=r"(v.y), "=r"(v.z), "=r"(v.w) : "r"(a) : "memory"); return v; }
__device__ __forceinline__ float2 lds2f(uint32_t a) { float2 v; asm volatile("ld.shared.v2.f32 {%0,%1}, [%2];" : "=f"(v.x), "=f"(v.y) : "r"(a) : "memory"); return v; }
__device__ __forceinline__ uint32_t lds1(uint32_t a) { uint32_t v; asm volatile("ld.shared.u32 %0, [%1];" : "=r"(v) : "r"(a) : "memory"); return v; }
__device__ __forceinline__ void sts4(uint32_t a, uint4 v) { asm volatile("st.shared.v4.u32 [%0], {%1,%2,%3,%4};" ::"r"(a), "r"(v.x), "r"(v.y), "r"(v.z), "r"(v.w) : "memory"); }
__device__ __forceinline__ void sts2(uint32_t a, uint32_t x, uint32_t y) { asm volatile("st.shared.v2.u32 [%0], {%1,%2};" ::"r"(a), "r"(x), "r"(y) : "memory"); }
__device__ __forceinline__ void sts1(uint32_t a, uint32_t v) { asm volatile("st.shared.u32 [%0], %1;" ::"r"(a), "r"(v) : "memory"); }
__device__ __forceinline__ void stsm4(uint32_t a, uint32_t r0, uint32_t r1, uint32_t r2, uint32_t r3) {
    asm volatile("stmatrix.sync.aligned.m8n8.x4.shared.b16 [%0], {%1,%2,%3,%4};" ::"r"(a), "r"(r0), "r"(r1), "r"(r2), "r"(r3));
}
__device__ __forceinline__ uint32_t pack2(float lo, float hi) { uint32_t r; asm("cvt.rn.bf16x2.f32 %0, %1, %2;" : "=r"(r) : "f"(hi), "f"(lo)); return r; }
__device__ __forceinline__ uint32_t pack2_relu(float lo, float hi) { uint32_t r; asm("cvt.rn.relu.bf16x2.f32 %0, %1, %2;" : "=r"(r) : "f"(hi), "f"(lo)); return r; }
__device__ __forceinline__ uint32_t hfma2(uint32_t a, uint32_t b, uint32_t c) { uint32_t r; asm("fma.rn.bf16x2 %0, %1, %2, %3;" : "=r"(r) : "r"(a), "r"(b), "r"(c)); return r; }
__device__ __forceinline__ uint32_t hmul2(uint32_t a, uint32_t b) { uint32_t r; asm("mul.rn.bf16x2 %0, %1, %2;" : "=r"(r) : "r"(a), "r"(b)); return r; }
__device__ __forceinline__ float bf_lo(uint32_t v) { return __uint_as_float(v << 16); }
__device__ __forceinline__ float bf_hi(uint32_t v) { return __uint_as_float(v & 0xFFFF0000u); }
__device__ __forceinline__ float bf_round(float v) { return bf_lo(pack2(v, 0.f)); }
__device__ __forceinline__ float ex2(float x) { float r; asm("ex2.approx.ftz.f32 %0, %1;" : "=f"(r) : "f"(x)); return r; }
__device__ __forceinline__ void mma16816(float* d, uint32_t a0, uint32_t a1, uint32_t a2, uint32_t a3, uint32_t b0, uint32_t b1) {
    asm("mma.sync.aligned.m16n8k16.row.col.f32.bf16.bf16.f32 {%0,%1,%2,%3}, {%4,%5,%6,%7}, {%8,%9}, {%0,%1,%2,%3};"
        : "+f"(d[0]), "+f"(d[1]), "+f"(d[2]), "+f"(d[3]) : "r"(a0), "r"(a1), "r"(a2), "r"(a3), "r"(b0), "r"(b1));
}
__device__ __forceinline__ void mma16816_first(float* d, uint32_t a0, uint32_t a1, uint32_t a2, uint32_t a3, uint32_t b0, uint32_t b1) {
    asm volatile("mma.sync.aligned.m16n8k16.row.col.f32.bf16.bf16.f32 {%0,%1,%2,%3}, {%4,%5,%6,%7}, {%8,%9}, {%10,%10,%10,%10};"
        : "=f"(d[0]), "=f"(d[1]), "=f"(d[2]), "=f"(d[3]) : "r"(a0), "r"(a1), "r"(a2), "r"(a3), "r"(b0), "r"(b1), "f"(0.f));
}
__device__ __forceinline__ void mma16816_v(float* d, uint32_t a0, uint32_t a1, uint32_t a2, uint32_t a3, uint32_t b0, uint32_t b1) {
    asm volatile("mma.sync.aligned.m16n8k16.row.col.f32.bf16.bf16.f32 {%0,%1,%2,%3}, {%4,%5,%6,%7}, {%8,%9}, {%0,%1,%2,%3};"
        : "+f"(d[0]), "+f"(d[1]), "+f"(d[2]), "+f"(d[3]) : "r"(a0), "r"(a1), "r"(a2), "r"(a3), "r"(b0), "r"(b1));
}
__device__ __forceinline__ void mma1688(float* d, uint32_t a0, uint32_t a1, uint32_t b0) {
    asm("mma.sync.aligned.m16n8k8.row.col.f32.bf16.bf16.f32 {%0,%1,%2,%3}, {%4,%5}, {%6}, {%0,%1,%2,%3};"
        : "+f"(d[0]), "+f"(d[1]), "+f"(d[2]), "+f"(d[3]) : "r"(a0), "r"(a1), "r"(b0));
}
__device__ __forceinline__ void ldsm4(uint32_t a, uint32_t* r) {
    asm volatile("ldmatrix.sync.aligned.m8n8.x4.shared.b16 {%0,%1,%2,%3}, [%4];" : "=r"(r[0]), "=r"(r[1]), "=r"(r[2]), "=r"(r[3]) : "r"(a));
}
__device__ __forceinline__ void ldsm4t(uint32_t a, uint32_t* r) {
    asm volatile("ldmatrix.sync.aligned.m8n8.x4.trans.shared.b16 {%0,%1,%2,%3}, [%4];" : "=r"(r[0]), "=r"(r[1]), "=r"(r[2]), "=r"(r[3]) : "r"(a));
}
__device__ __forceinline__ float rcp(float x) { float r; asm("rcp.approx.ftz.f32 %0, %1;" : "=f"(r) : "f"(x)); return r; }
__device__ __forceinline__ uint2 ld_relaxed2(const void* p) { uint2 v; asm volatile("ld.relaxed.gpu.global.v2.u32 {%0,%1}, [%2];" : "=r"(v.x), "=r"(v.y) : "l"(p) : "memory"); return v; }
__device__ __forceinline__ void st_relaxed2(void* p, uint32_t x, uint32_t y) { asm volatile("st.relaxed.gpu.global.v2.u32 [%0], {%1,%2};" ::"l"(p), "r"(max(x, 1u)), "r"(max(y, 1u)) : "memory"); }
__host__ __device__ constexpr uint64_t dconst(uint32_t lbo, uint32_t sbo, uint32_t swz) {
    return ((uint64_t)(lbo >> 4) << 16) | ((uint64_t)(sbo >> 4) << 32) | ((uint64_t)swz << 62);
}
__device__ __forceinline__ uint32_t mkdesc(uint32_t addr, uint64_t c) { return (uint32_t)c | ((addr & 0x3FFFF) >> 4); }
#define WG_FENCE() asm volatile("wgmma.fence.sync.aligned;" ::: "memory")
#define WG_COMMIT() asm volatile("wgmma.commit_group.sync.aligned;" ::: "memory")
#define WG_WAIT(n) asm volatile("wgmma.wait_group.sync.aligned %0;" ::"n"(n) : "memory")
template <int N> __device__ __forceinline__ void reg_fence(float* d) {
#pragma unroll
    for (int i = 0; i < N; i++) asm volatile("" : "+f"(d[i])::"memory");
}
template <int N> __device__ __forceinline__ void reg_def(float* d) {
#pragma unroll
    for (int i = 0; i < N; i++) asm volatile("" : "=f"(d[i]));
}
template <int N> __device__ __forceinline__ void reg_def(uint32_t* d) {
#pragma unroll
    for (int i = 0; i < N; i++) asm volatile("" : "=r"(d[i]));
}
__device__ __forceinline__ bool is_unset(uint4 v) { return min(min(v.x, v.y), min(v.z, v.w)) == 0u; }
__device__ __forceinline__ uint4 nz4(uint32_t a, uint32_t b, uint32_t c, uint32_t d) { return make_uint4(max(a, 1u), max(b, 1u), max(c, 1u), max(d, 1u)); }
__device__ __forceinline__ void wait_flags(const uint32_t* p, uint32_t target, uint32_t mask) {
    int n = 0;
    while (~__ballot_sync(~0u, (int)(ld_relaxed(p) - target) >= 0) & mask) { if (++n > SPIN_LIMIT) __trap(); }
    asm volatile("fence.acquire.gpu;" ::: "memory");
}
__device__ __forceinline__ float silu_bf(uint32_t cbits) {
    const float c = __uint_as_float(cbits << 16);
    return bf_round(__fdividef(c, 1.f + fminf(ex2(-1.4426950408889634f * c), 1e30f)));
}
__device__ __forceinline__ void gemv_part(uint32_t wmbuf, int npanel, int wp, int lane) {
    const uint32_t wa = wmbuf + wp * 512 + (8 * (lane >> 4) + (lane & 7)) * 32 + ((lane >> 3) & 1) * 16;
    uint2 B[4];
#pragma unroll
    for (int i = 0; i < 4; i++) { const float2 v = lds2f(wmbuf + 28672 + (wp + 8 * i) * 32 + (lane & 3) * 8); B[i] = make_uint2(__float_as_uint(v.x), __float_as_uint(v.y)); }
#pragma unroll 1
    for (int pn = 0; pn < npanel; pn++) {
        float d[4] = {};
        uint32_t A[16];
#pragma unroll
        for (int i = 0; i < 4; i++) ldsm4t(wa + pn * 14336 + (i < 3 || wp < 4 ? i : 0) * 4096, A + 4 * i);
#pragma unroll
        for (int i = 0; i < 4; i++) mma16816(d, A[4 * i], A[4 * i + 1], A[4 * i + 2], A[4 * i + 3], B[i].x, B[i].y);
        if ((lane & 3) == 0) {
            sts1(wmbuf + 29696 + (wp * 32 + pn * 16 + (lane >> 2)) * 4, __float_as_uint(d[0]));
            sts1(wmbuf + 29696 + (wp * 32 + pn * 16 + 8 + (lane >> 2)) * 4, __float_as_uint(d[2]));
        }
    }
}
__device__ __forceinline__ int pass_f(int fs, int ps) { return 224 * fs + ((fs & 1) ? (ps == 0 ? 96 : ps == 1 ? 32 : 0) : (ps == 0 ? 0 : ps == 1 ? 128 : 192)); }
__device__ __forceinline__ constexpr uint32_t slot_off(int l) { return (l < 3 || l > 6 ? l : l == 6 ? 3 : l + 1) * 16384; }
__device__ __forceinline__ void ln_coeffs(float mean, float msq, uint32_t& r2, uint32_t& n2) {
    const float rs = bf_round(rsqrtf(fmaxf(msq - mean * mean, 0.f) + 1e-5f));
    r2 = pack2(rs, rs);
    n2 = pack2(-mean * rs, -mean * rs);
}

#define LOADW bulk_e(dst, g_wd + (size_t)((f >> 5) * 4 + nq) * 1792, 7168, bar);
template <int sec> __device__ __forceinline__ void ring_loader(const Params& p, uint32_t sb_, int r_, int j_, int lane) {
    const uint32_t sb = opaque(sb_);
    const int r = opaque(r_), j = opaque(j_), nq = j >> 1, fs = 4 * (j & 1) + nq;
    const int fa = pass_f(fs, 0), fb = pass_f(fs, 1), fc = pass_f(fs, 2);
#define BAR(i) (sb + M_BAR + 8 * (i))
#define kh (j & 1)
            int sl = 0;
            mbar_wait(BAR(B_PUB + 2), 0);
            wait_flags(g_flag + (8 * r + j) * 128 + 96 + lane, lds1(sb + M_EPOCH) + 1, 0xFFFFu);
            fence_async_global();
#pragma unroll 1
            for (int s = 0; s < 28; s++) {
                if (s >= 1 && s < 6) mbar_wait(BAR(B_FULL + s - 1), 0);
                const int ps = s < 14 ? 0 : s < 21 ? 1 : 2;
                const uint32_t half = ps < 2 ? 8192 : 4096;
                mbar_wait(BAR(B_EMPTY + sl), (s >= 7 && s < 14) || s >= 21);
                expect_e(BAR(B_FULL + sl), half);
                tma3_e(sb + slot_off(sl) + sec * half, &p.ga + 2 * ps + sec, 0, ps ? 64 * sl : 32 * s, ps == 0 ? fa >> 6 : ps == 1 ? fb >> 6 : fc >> 5, BAR(B_FULL + sl));
                sl = sl == 6 ? 0 : sl + 1;
            }
            if (!sec) PROFH(3);
#pragma unroll 1
            for (int e = 0; e < 4; e++) {
                const uint32_t dst = sb + slot_off(e) + sec * 8192, bar = BAR(B_FULL + e);
                const int f = (e < 2 ? fa + 64 * e : e == 2 ? fb : fc) + 32 * sec;
                mbar_wait(BAR(B_EMPTY + e), 0);
                expect_e(bar, e == 3 && sec ? 0 : 7168);
                if (!(e == 3 && sec)) { LOADW }
            }
            sl = 4;
            int e = 4;
#pragma unroll 1
            for (int grp = 0; grp < 9; grp++) {
                const int ps = grp >= 6 ? 2 : grp >= 3 ? 1 : 0;
                int sidx = grp - 3 * ps;
                if (sec && sidx == 0) { mbar_wait(BAR(B_HRDY + ps), 0); fence_async_global(); }
                sidx += sidx >= nq;
                int f = pass_f(4 * kh + sidx, ps);
#pragma unroll 1
                for (int k = 4 >> ps; k > 0; k--, e++, f += 32) {
                    const uint32_t dst = sb + slot_off(sl), bar = BAR(B_FULL + sl);
                    mbar_wait(BAR(B_EMPTY + sl), e >= 12 && e < 24);
                    if (e < WIN_END && e >= WIN) mbar_wait(BAR(B_FULL + (sl >= WIN ? sl - WIN : sl + 12 - WIN)), e - WIN >= 12);
                    expect_e(bar, sec ? 8192 : 7168);
                    if (!sec) { LOADW }
                    else bulk_e(dst + 8192, g_h2 + (size_t)r * (224 * 512) + f * 64, 8192, bar);
                    sl = sl == 11 ? 0 : sl + 1;
                }
            }
            if (!sec) PROFH(4);
}

__global__ void __cluster_dims__(2, 1, 1) __launch_bounds__(384, 1) fused_block_kernel(const __grid_constant__ Params p) {
    extern __shared__ __align__(1024) unsigned char smem[];
    const uint32_t sb = (uint32_t)__cvta_generic_to_shared(smem);
    const int tid = threadIdx.x, lane = tid & 31, warp = __shfl_sync(~0u, tid >> 5, 0);
    const int m = blockIdx.x >> 1;
    int r, nq;
    {
        int g, i;
        if (m < MAP_S) { g = m < 4 ? 15 : 16; i = m & 3; }
        else if (m < MAP_S + 32) { g = (m - MAP_S) & 7; i = (m - MAP_S) >> 3; }
        else if (m < MAP_S + 60) { i = (m - MAP_S - 32) / 7; g = 8 + (m - MAP_S - 32) - 7 * i; }
        else { g = 16; i = m & 3; }
        r = g; nq = i;
    }
    const int j = opaque(2 * nq + (blockIdx.x & 1)), b = 8 * r + j, fs = 4 * kh + nq;
    const uint32_t sc = r == 16;
    if (lane == 0 && warp < 9 && warp != 6 && warp != 7) {
        const int i0 = warp == 8 ? 0 : 8 + 8 * warp, cnt = warp == 0 || warp == 8 ? 1 : warp < 3 ? 2 : 8;
#pragma unroll
        for (int k = 0; k < 8; k++) if (i0 + k != B_WMFULL) mbar_init(BAR(i0 + k), cnt);
        asm volatile("fence.mbarrier_init.release.cluster;" ::: "memory");
        fence_async_smem();
    }

    if (warp < 8) {
        const int w = warp >> 2, wi = warp & 3;
#define COORDS const int t = fresh_tid() & 127, lane = t & 31, q = lane & 3, lr = lane >> 2, ra = 64 * w + 16 * wi + lr; \
        const uint32_t lx = (lane >> 4) ^ (lane & 7), mrow = (64 * w + 16 * wi + ((lane >> 3) & 1) * 8 + (lane & 7)) * 128; \
        (void)q; (void)lr; (void)ra; (void)lx; (void)mrow;
        const int sid = 2 * (j & 3) + w;
#define RUN(k) (!sc || sid == (k))
#define WAIT(i, par) mbar_wait_c(BAR(i), (par) | sc)
        constexpr uint64_t DB128 = dconst(4096, 1024, 1);
        bar_arrive(9, 384);
        bar_sync(0, 384);
        asm volatile("barrier.cluster.arrive.relaxed.aligned;" ::: "memory");
        asm volatile("setmaxnreg.inc.sync.aligned.u32 224;");
        PROFC(0);
        uint32_t xr[16];
        {
            COORDS
            uint32_t h[112];
            if (RUN(0)) {
                float ds[4] = {}, da[2][4] = {}, db[2][4] = {};
                const uint32_t ONE2 = 0x3F803F80u;
                if (kh == 0) { WAIT(B_WMFULL, 0); gemv_part(sb + OFF_Y + HALF, 1, warp, lane); warp_arrive(BAR(B_GEMV)); }
#pragma unroll
                for (int kb = 0; kb < 7; kb++) {
                    WAIT(B_XFULL + kb, 0);
#pragma unroll
                    for (int k4 = 0; k4 < 4; k4++) ldsm4(sb + OFF_X + mrow + kb * 16384 + (((2 * k4) ^ lx) << 4), h + 16 * kb + 4 * k4);
#pragma unroll
                    for (int k4 = 0; k4 < 4; k4++) {
                        const uint32_t* f = h + 16 * kb + 4 * k4;
                        mma16816(ds, f[0], f[1], f[2], f[3], ONE2, ONE2);
                        mma1688(da[0], f[0], f[1], f[0]); mma1688(db[0], f[0], f[1], f[1]);
                        mma1688(da[1], f[2], f[3], f[2]); mma1688(db[1], f[2], f[3], f[3]);
                    }
                }
#pragma unroll
                for (int i = 0; i < 4; i++) {
                    const int ch = 7 * j + 2 * i + (lane >> 4);
                    ldsm4(sb + OFF_X + mrow + (ch >> 3) * 16384 + (((ch ^ lane) & 7) << 4), xr + 4 * i);
                }
                warp_arrive(BAR(B_XFREE));
                float qa = (lr & 1) ? da[0][1] + da[1][1] : da[0][0] + da[1][0];
                float qb = (lr & 1) ? db[0][3] + db[1][3] : db[0][2] + db[1][2];
                const int src = (lane & ~3) | (lr >> 1);
                qa = __shfl_sync(~0u, qa, src);
                qb = __shfl_sync(~0u, qb, src);
                uint32_t ra2, na2, rb2, nb2;
                ln_coeffs(ds[0] * (1.f / DM), qa * (1.f / DM), ra2, na2);
                ln_coeffs(ds[2] * (1.f / DM), qb * (1.f / DM), rb2, nb2);
#pragma unroll
                for (int i = 0; i < 112; i += 2) { h[i] = hfma2(h[i], ra2, na2); h[i + 1] = hfma2(h[i + 1], rb2, nb2); }
                if (kh == 1) { WAIT(B_WMFULL, 0); gemv_part(sb + OFF_Y + HALF, 2, warp, lane); warp_arrive(BAR(B_GEMV)); }
            } else { reg_def<112>(h); reg_def<16>(xr); }
            PROFC(1);
            if (RUN(1)) {
                float ak[28], av[28], aq[28];
                uint32_t kp[14], vp[14];
                const uint32_t bk0 = mkdesc(sb + OFF_Y, DB128) + kh, bv0 = mkdesc(sb + OFF_Y + HALF, DB128) + kh, bq0 = mkdesc(sb + OFF_X, DB128) + kh;
                uint32_t* kvg = g_kv + (size_t)(b * 2) * 3584 + (8 * w + 2 * wi) * 224 + lane;
                WAIT(B_FULLK, 0);
                WAIT(B_MOD1, 0);
                PROFC(2);
                reg_def<28>(ak);
#pragma unroll
                for (int g4 = 0; g4 < 4; g4++) {
#pragma unroll
                    for (int ks = 7 * g4; ks < 7 * g4 + 7; ks++) {
                        const uint4 st = *(const uint4*)(smem + M_ST + ks * 64 + q * 16);
                        h[4 * ks] = hfma2(h[4 * ks], st.x, st.y); h[4 * ks + 1] = hfma2(h[4 * ks + 1], st.x, st.y);
                        h[4 * ks + 2] = hfma2(h[4 * ks + 2], st.z, st.w); h[4 * ks + 3] = hfma2(h[4 * ks + 3], st.z, st.w);
                    }
                    WG_FENCE();
#pragma unroll
                    for (int ks = 7 * g4; ks < 7 * g4 + 7; ks++) wgmma_rs_56<DB128>(ak, h[4 * ks], h[4 * ks + 1], h[4 * ks + 2], h[4 * ks + 3], bk0 + ks * 128, ks != 0);
                }
                WG_COMMIT();
                PROFC(3);
                WAIT(B_FULLV, 0);
                reg_def<28>(av);
                WG_FENCE();
#pragma unroll
                for (int ks = 0; ks < 8; ks++) wgmma_rs_56<DB128>(av, h[4 * ks], h[4 * ks + 1], h[4 * ks + 2], h[4 * ks + 3], bv0 + ks * 128, ks != 0);
                WG_COMMIT();
                WG_WAIT(1);
                reg_fence<28>(ak);
#pragma unroll
                for (int g = 0; g < 7; g++) {
                    kp[2 * g] = pack2(ak[4 * g], ak[4 * g + 1]); kp[2 * g + 1] = pack2(ak[4 * g + 2], ak[4 * g + 3]);
                    kvg[g * 32] = kp[2 * g]; kvg[224 + g * 32] = kp[2 * g + 1];
                }
                warp_arrive(BAR(B_PUB));
                PROFC(4);
                WG_FENCE();
#pragma unroll
                for (int ks = 8; ks < 28; ks++) wgmma_rs_56<DB128>(av, h[4 * ks], h[4 * ks + 1], h[4 * ks + 2], h[4 * ks + 3], bv0 + ks * 128, 1);
                WG_COMMIT();
                WAIT(B_FULLQ, 0);
                reg_def<28>(aq);
                WG_FENCE();
#pragma unroll
                for (int ks = 0; ks < 8; ks++) wgmma_rs_56<DB128>(aq, h[4 * ks], h[4 * ks + 1], h[4 * ks + 2], h[4 * ks + 3], bq0 + ks * 128, ks != 0);
                WG_COMMIT();
                WG_WAIT(1);
                reg_fence<28>(av);
#pragma unroll
                for (int g = 0; g < 7; g++) {
                    vp[2 * g] = pack2(av[4 * g], av[4 * g + 1]); vp[2 * g + 1] = pack2(av[4 * g + 2], av[4 * g + 3]);
                    kvg[3584 + g * 32] = vp[2 * g]; kvg[3584 + 224 + g * 32] = vp[2 * g + 1];
                }
                warp_arrive(BAR(B_PUB + 1));
                PROFC(5);
                WG_FENCE();
#pragma unroll
                for (int ks = 8; ks < 28; ks++) wgmma_rs_56<DB128>(aq, h[4 * ks], h[4 * ks + 1], h[4 * ks + 2], h[4 * ks + 3], bq0 + ks * 128, 1);
                WG_COMMIT();
                WAIT(B_PUB + 1, 0);
                const uint32_t ko = sb + OFF_Y + Y_KOWN + (8 * w + 2 * wi) * 896 + lane * 4;
                const uint32_t qo = sb + OFF_Y + Y_Q + (8 * w + 2 * wi) * 1024 + lane * 4;
#pragma unroll
                for (int g = 0; g < 7; g++) {
                    sts1(ko + g * 128, kp[2 * g]); sts1(ko + 896 + g * 128, kp[2 * g + 1]);
                    sts1(ko + (Y_VOWN - Y_KOWN) + g * 128, vp[2 * g]); sts1(ko + (Y_VOWN - Y_KOWN) + 896 + g * 128, vp[2 * g + 1]);
                }
                WG_WAIT(0);
                reg_fence<28>(aq);
                __syncwarp();
                if (lane < 3 && w == 1) mbar_arrive(BAR(B_EMPTY + lane));
#pragma unroll
                for (int g = 0; g < 7; g++) {
                    const uint32_t q0 = pack2(aq[4 * g], aq[4 * g + 1]), q1 = pack2(aq[4 * g + 2], aq[4 * g + 3]);
                    if (g == 3) {
                        sts1(qo + 3 * 128, q < 2 ? q0 : 0u); sts1(qo + 1024 + 3 * 128, q < 2 ? q1 : 0u);
                        sts1(qo + 4 * 128, q < 2 ? 0u : q0); sts1(qo + 1024 + 4 * 128, q < 2 ? 0u : q1);
                    } else {
                        const int ch = g < 3 ? g : g + 1;
                        sts1(qo + ch * 128, q0); sts1(qo + 1024 + ch * 128, q1);
                    }
                }
                if (!sc) bar_sync(3, 256);
            }
        }
        PROFC(6);
        WAIT(B_KRFULL, 0);
        PROFC(7);
        if (RUN(2)) {
#pragma unroll 1
            for (int hf = sc; hf < 2; hf++) {
                COORDS
                float s[136];
                float na = 0.f, nb = 0.f;
                const float CS = 0.18898223650461361f * 1.4426950408889634f;
                const int kg0 = 8 * hf + 2 * wi;
                const int pmin = 16 - 8 * r - 4 * hf - wi;
                const float NEG = __int_as_float(0xFF800000);
                {
                    uint32_t F[8];
                    const uint32_t qa = sb + OFF_Y + Y_Q + (kg0 + ((lane >> 3) & 1)) * 1024 + (4 * w + (lane >> 4)) * 128 + (lane & 7) * 16;
                    ldsm4(qa, F); ldsm4(qa + 256, F + 4);
                    uint32_t ka = sb + OFF_Y + Y_K + kg0 * 896 + (3 * w + (lane >> 3)) * 128 + (lane & 7) * 16;
#pragma unroll
                    for (int g = 0; g < 34; g++) {
                        uint32_t B[4];
                        if (g >= 12 && g % 4 == 0) ka += __float_as_uint(s[4 * (g - 12)]) & p.zero;
                        ldsm4(ka + g * 896, B);
                        mma16816_first(s + 4 * g, F[0], F[1], F[2], F[3], B[0], B[1]);
                        mma16816_v(s + 4 * g, F[4], F[5], F[6], F[7], B[2], B[3]);
                    }
                    const bool c0 = 2 * q > lr, c1 = 2 * q + 1 > lr;
                    if (!c0) { s[0] = NEG; s[6] = NEG; }
                    if (!c1) { s[1] = NEG; s[7] = NEG; }
                    s[2] = NEG; s[3] = NEG;
                    if (c0) { s[128] = NEG; s[134] = NEG; }
                    if (c1) { s[129] = NEG; s[135] = NEG; }
                    s[132] = NEG; s[133] = NEG;
                    float ma = NEG, mb = NEG;
#pragma unroll
                    for (int pp = 0; pp < 17; pp++) {
                        const float* e = s + 8 * pp;
                        const float bias = pp < pmin ? NEG : 0.f;
                        ma = fmaxf(ma, fmaxf(fmaxf(e[0], e[1]), fmaxf(e[4], e[5])) + bias);
                        mb = fmaxf(mb, fmaxf(fmaxf(e[2], e[3]), fmaxf(e[6], e[7])) + bias);
                    }
                    ma = fmaxf(ma, __shfl_xor_sync(~0u, ma, 1)); mb = fmaxf(mb, __shfl_xor_sync(~0u, mb, 1));
                    ma = fmaxf(ma, __shfl_xor_sync(~0u, ma, 2)); mb = fmaxf(mb, __shfl_xor_sync(~0u, mb, 2));
                    na = -ma * CS; nb = -mb * CS;
                }
                PROFC(8 + 3 * hf);
                {
                    WAIT(B_VRFULL, 0);
                    float o[16] = {}, rs[4] = {};
                    uint32_t pk[2];
                    const uint32_t va = sb + OFF_Y + Y_VR + (kg0 + ((lane >> 3) & 1)) * 896 + (3 * w + (lane >> 4)) * 128 + (lane & 7) * 16;
#pragma unroll
                    for (int pp = 0; pp < 17; pp++) {
                        uint32_t B[8];
                        const uint32_t v = va + pp * 1792 + (pp == 16 || (pp >= 9 && kg0 + 2 * pp >= 32) ? Y_VOWN - 32 * 896 : 0);
                        ldsm4t(v, B); ldsm4t(v + 256, B + 4);
                        float e[8];
                        const float bias = __uint_as_float((pp < pmin ? 0xFF800000u : 0u) | ((pp < 2 ? B[0] : pk[pp & 1]) & p.zero));
#pragma unroll
                        for (int i = 0; i < 8; i++) e[i] = ex2(fmaf(s[8 * pp + i], CS, ((i & 2) ? nb : na) + bias));
                        const uint32_t p0 = pack2(e[0], e[1]), p1 = pack2(e[2], e[3]), p2 = pack2(e[4], e[5]), p3 = pack2(e[6], e[7]);
                        pk[pp & 1] = p3;
                        mma16816(rs, p0, p1, p2, p3, 0x3F803F80u, 0x3F803F80u);
#pragma unroll
                        for (int g = 0; g < 4; g++) mma16816(o + 4 * g, p0, p1, p2, p3, B[2 * g], B[2 * g + 1]);
                    }
                    PROFC(9 + 3 * hf);
                    const float ia = rcp(rs[0]), ib = rcp(rs[2]);
                    uint32_t* og = g_o + (size_t)(2 * r + hf) * 14336 + (7 * j + 3 * w) * 256 + wi * 64 + lane;
#pragma unroll
                    for (int g = 0; g < 4; g++) {
                        if ((g == 3 - 3 * w) ? ((q >> 1) == w) : true) {
                            og[g * 256] = pack2(o[4 * g] * ia, o[4 * g + 1] * ia);
                            og[g * 256 + 32] = pack2(o[4 * g + 2] * ib, o[4 * g + 3] * ib);
                        }
                    }
                    warp_arrive(BAR(B_PUB + 2 + hf));
                    PROFC(10 + 3 * hf);
                }
            }
        }
        uint32_t x1p[14];
        COORDS
        constexpr uint64_t DT = dconst(1024, 128, 0);
        if (RUN(4)) {
            float ac[28];
            const uint32_t ad = mkdesc(sb + (w ? OFF_Y + HALF : OFF_X), DT), bd = mkdesc(sb + OFF_X + HALF, DB128) + kh;
            WAIT(B_WOFULL, 0);
            WAIT(B_MOD2, 0);
            WAIT(B_GFULL + w, 0);
            PROFC(28);
            reg_def<28>(ac);
#pragma unroll 1
            for (int u = 0; u < 4; u++) {
                WG_FENCE();
#pragma unroll
                for (int i = 0; i < 7; i++) wgmma_ss_56<DT, DB128>(ac, ad + (7 * u + i) * 128, bd + (7 * u + i) * 128, (u | i) != 0);
            }
            WG_COMMIT();
            WG_WAIT(0);
            reg_fence<28>(ac);
            PROFC(14);
            __syncwarp();
            if (lane < 3) mbar_arrive(BAR(B_EMPTY + 3 + lane));
            if (lane < 3 && w == 0) mbar_arrive(BAR(B_EMPTY + lane));
            float s1a = 0.f, s2a = 0.f, s1b = 0.f, s2b = 0.f;
            uint32_t* xo = g_x1 + (size_t)(2 * r + w) * 14336 + 7 * j * 256 + wi * 64 + lane;
#pragma unroll
            for (int g = 0; g < 7; g++) {
                const float2 ga = *(const float2*)(smem + M_G + (8 * g + 2 * q) * 4);
                x1p[2 * g] = pack2(fmaf(ga.x, ac[4 * g], bf_lo(xr[2 * g])), fmaf(ga.y, ac[4 * g + 1], bf_hi(xr[2 * g])));
                x1p[2 * g + 1] = pack2(fmaf(ga.x, ac[4 * g + 2], bf_lo(xr[2 * g + 1])), fmaf(ga.y, ac[4 * g + 3], bf_hi(xr[2 * g + 1])));
                xo[g * 256] = x1p[2 * g]; xo[g * 256 + 32] = x1p[2 * g + 1];
                const float u0 = bf_lo(x1p[2 * g]), u1 = bf_hi(x1p[2 * g]), u2 = bf_lo(x1p[2 * g + 1]), u3 = bf_hi(x1p[2 * g + 1]);
                s1a += u0 + u1; s2a += u0 * u0 + u1 * u1; s1b += u2 + u3; s2b += u2 * u2 + u3 * u3;
            }
            float ka = (q & 1) ? s2a : s1a, kb2 = (q & 1) ? s2b : s1b;
            ka += __shfl_xor_sync(~0u, (q & 1) ? s1a : s2a, 1); kb2 += __shfl_xor_sync(~0u, (q & 1) ? s1b : s2b, 1);
            const float kk = ((q & 2) ? kb2 : ka) + __shfl_xor_sync(~0u, (q & 2) ? ka : kb2, 2);
            ((float*)g_st)[(((2 * r + w) * 8 + j) * 64 + 16 * wi + lr + 4 * (q & 2)) * 2 + (q & 1)] = kk;
            __syncwarp();
            if (lane < 2) mbar_arrive(BAR(B_PUB + 4 + w));
        } else reg_def<14>(x1p);
        PROFC(15);
        uint32_t h2a[32], h2b[24];
        if (RUN(6)) {
            const int fa = pass_f(fs, 0), fb = pass_f(fs, 1), fc = pass_f(fs, 2);
            uint32_t* h2g = g_h2 + (size_t)r * (224 * 512) + (8 * w + 2 * wi) * 32 + lane;
            const uint32_t a0 = mkdesc(sb + OFF_Y + w * HALF, DT);
            {
                WAIT(B_GFULL + 2 + w, 0);
                PROFC(16);
                float2 sa = make_float2(0.f, 0.f), sbb = sa;
#pragma unroll
                for (int jj = 0; jj < 8; jj++) {
                    const float2 u = lds2f(sb + OFF_X + X_STAT + w * 4096 + (jj * 64 + 16 * wi + lr) * 8), v = lds2f(sb + OFF_X + X_STAT + w * 4096 + (jj * 64 + 16 * wi + lr + 8) * 8);
                    sa.x += u.x; sa.y += u.y; sbb.x += v.x; sbb.y += v.y;
                }
                warp_arrive(BAR(B_EMPTY + 6));
                uint32_t ra2, na2, rb2, nb2;
                ln_coeffs(sa.x * (1.f / DM), sa.y * (1.f / DM), ra2, na2);
                ln_coeffs(sbb.x * (1.f / DM), sbb.y * (1.f / DM), rb2, nb2);
                const uint32_t ha = sb + OFF_Y + w * HALF + (lane >> 4) * 1024 + (2 * wi + ((lane >> 3) & 1)) * 128 + (lane & 7) * 16;
                const uint32_t sta = sb + M_ST + q * 16;
                auto prep = [&](int s, uint32_t* f) {
                    uint32_t x[8];
                    ldsm4(ha + s * 4096, x); ldsm4(ha + s * 4096 + 2048, x + 4);
                    const uint4 st[2] = {lds4(sta + s * 128), lds4(sta + s * 128 + 64)};
#pragma unroll
                    for (int i = 0; i < 2; i++) {
                        f[4 * i] = hfma2(hfma2(x[4 * i], ra2, na2), st[i].x, st[i].y); f[4 * i + 1] = hfma2(hfma2(x[4 * i + 1], rb2, nb2), st[i].x, st[i].y);
                        f[4 * i + 2] = hfma2(hfma2(x[4 * i + 2], ra2, na2), st[i].z, st[i].w); f[4 * i + 3] = hfma2(hfma2(x[4 * i + 3], rb2, nb2), st[i].z, st[i].w);
                    }
                    stsm4(ha + s * 4096, f[0], f[1], f[2], f[3]); stsm4(ha + s * 4096 + 2048, f[4], f[5], f[6], f[7]);
                };
                float ac[128];
                uint32_t fr[3][8];
                const uint32_t bx = mkdesc(sb, DB128);
                reg_def<128>(ac);
                prep(0, fr[0]);
                PROFC(17);
#pragma unroll
                for (int s = 0; s < 14; s++) {
                    const uint32_t* f = fr[s % 3];
                    const uint32_t bd = bx + (slot_off(s % 7) >> 4);
                    WAIT(B_FULL + s % 7, s >= 7);
                    WG_FENCE();
                    wgmma_rs_256<DB128>(ac, f[0], f[1], f[2], f[3], bd, s != 0);
                    wgmma_rs_256<DB128>(ac, f[4], f[5], f[6], f[7], bd + 128, 1);
                    WG_COMMIT();
                    if (s < 13) prep(s + 1, fr[(s + 1) % 3]);
                    if (s > 0) { WG_WAIT(1); warp_arrive(BAR(B_EMPTY + (s - 1) % 7)); }
                }
                PROFC(18);
                fence_async_smem();
                WG_WAIT(0);
                reg_fence<128>(ac);
                warp_arrive(BAR(B_EMPTY + 6));
#pragma unroll
                for (int g = 0; g < 16; g++) {
                    h2a[2 * g] = hmul2(pack2_relu(ac[4 * g], ac[4 * g + 1]), pack2(ac[64 + 4 * g], ac[64 + 4 * g + 1]));
                    h2a[2 * g + 1] = hmul2(pack2_relu(ac[4 * g + 2], ac[4 * g + 3]), pack2(ac[64 + 4 * g + 2], ac[64 + 4 * g + 3]));
                    h2g[(fa / 8 + g) * 512] = h2a[2 * g]; h2g[(fa / 8 + g) * 512 + 32] = h2a[2 * g + 1];
                }
                warp_arrive(BAR(B_PUB + 6));
                bar_sync(1 + w, 128);
            }
            PROFC(19);
            {
                float ac[64];
                reg_def<64>(ac);
                const uint32_t bx = mkdesc(sb, dconst(8192, 1024, 1));
#pragma unroll kB
                for (int s = 0; s < 7; s++) {
                    WAIT(B_FULL + s, 0);
                    const uint32_t ad = a0 + s * 512, bd = bx + (slot_off(s) >> 4);
                    WG_FENCE();
#pragma unroll
                    for (int k = 0; k < 4; k++) wgmma_ss_128<DT, DB128>(ac, ad + k * 128, bd + k * 128, (s | k) != 0);
                    WG_COMMIT();
                    if (s > 0) { WG_WAIT(1); warp_arrive(BAR(B_EMPTY + s - 1)); }
                }
                WG_WAIT(0);
                reg_fence<64>(ac);
                warp_arrive(BAR(B_EMPTY + 6));
#pragma unroll
                for (int g = 0; g < 8; g++) {
                    h2b[2 * g] = hmul2(pack2_relu(ac[4 * g], ac[4 * g + 1]), pack2(ac[32 + 4 * g], ac[32 + 4 * g + 1]));
                    h2b[2 * g + 1] = hmul2(pack2_relu(ac[4 * g + 2], ac[4 * g + 3]), pack2(ac[32 + 4 * g + 2], ac[32 + 4 * g + 3]));
                    h2g[(fb / 8 + g) * 512] = h2b[2 * g]; h2g[(fb / 8 + g) * 512 + 32] = h2b[2 * g + 1];
                }
                warp_arrive(BAR(B_PUB + 7));
            }
            PROFC(27);
            {
                float ac[32];
                reg_def<32>(ac);
                const uint32_t bx = mkdesc(sb, dconst(4096, 512, 2));
#pragma unroll kC
                for (int s = 0; s < 7; s++) {
                    WAIT(B_FULL + s, 1);
                    const uint32_t ad = a0 + p.zero + s * 512, bd = bx + (slot_off(s) >> 4);
                    WG_FENCE();
#pragma unroll
                    for (int k = 0; k < 4; k++) wgmma_ss_64<DT, dconst(4096, 512, 2)>(ac, ad + k * 128, bd + k * 64, (s | k) != 0);
                    WG_COMMIT();
                    if (s > 0) { WG_WAIT(1); warp_arrive(BAR(B_EMPTY + s - 1)); }
                }
                WG_WAIT(0);
                reg_fence<32>(ac);
                __syncwarp();
                if (lane < 6) mbar_arrive(BAR(B_EMPTY + 6 + lane));
                PROFC(20);
#pragma unroll
                for (int g = 0; g < 4; g++) {
                    h2b[16 + 2 * g] = hmul2(pack2_relu(ac[4 * g], ac[4 * g + 1]), pack2(ac[16 + 4 * g], ac[16 + 4 * g + 1]));
                    h2b[16 + 2 * g + 1] = hmul2(pack2_relu(ac[4 * g + 2], ac[4 * g + 3]), pack2(ac[16 + 4 * g + 2], ac[16 + 4 * g + 3]));
                    h2g[(fc / 8 + g) * 512] = h2b[16 + 2 * g]; h2g[(fc / 8 + g) * 512 + 32] = h2b[16 + 2 * g + 1];
                }
                warp_arrive(BAR(B_PUB + 8));
                asm volatile("barrier.cluster.wait.aligned;" ::: "memory");
                if (lane == 0 && !sc) {
                    uint32_t rb;
                    asm volatile("mapa.shared::cluster.u32 %0, %1, %2;" : "=r"(rb) : "r"(BAR(B_PEER)), "r"(kh ^ 1));
                    asm volatile("mbarrier.arrive.relaxed.cluster.shared::cluster.b64 _, [%0];" ::"r"(rb) : "memory");
                }
            }
        } else { reg_def<32>(h2a); reg_def<24>(h2b); }
        PROFC(21);
        if (RUN(7)) {
            float ac[56];
            reg_def<56>(ac);
            constexpr uint64_t DAN = dconst(2048, 128, 0);
            constexpr uint64_t DW = dconst(128, 512, 0);
            const uint32_t bx = mkdesc(sb, DW);
#pragma unroll
            for (int e = 0; e < 4; e++) {
                WAIT(B_FULL + e, 0);
                const uint32_t bd = bx + (slot_off(e) >> 4);
                const uint32_t* hh = e < 2 ? h2a + 16 * e : h2b + 16 * (e - 2);
                WG_FENCE();
#pragma unroll
                for (int k = 0; k < (e < 3 ? 4 : 2); k++) wgmma_rs_112<DW>(ac, hh[4 * k], hh[4 * k + 1], hh[4 * k + 2], hh[4 * k + 3], bd + (k >> 1) * 512 + (k & 1) * 16, (e | k) != 0);
                WG_COMMIT();
                if (e > 0) { WG_WAIT(1); warp_arrive(BAR(B_EMPTY + e - 1)); }
            }
            PROFC(22);
            const uint32_t ax = mkdesc(sb + 8192 + w * 1024, DAN);
#pragma unroll kG2
            for (int e = 4; e < 25; e++) {
                WAIT(B_FULL + e % 12, e >= 12 && e < 24);
                if (e == 16) PROFC(23);
                const uint32_t z = (e / 12) * p.zero;
                const uint32_t ad = ax + z + (slot_off(e % 12) >> 4), bd = bx + z + (slot_off(e % 12) >> 4);
                WG_FENCE();
                wgmma_ss_112<DAN, DW>(ac, ad, bd, 1);
                wgmma_ss_112<DAN, DW>(ac, ad + 256, bd + 16, 1);
                WG_COMMIT();
                if (e < 14) { WG_WAIT(1); warp_arrive(BAR(B_EMPTY + (e - 1) % 12)); }
            }
            mbar_wait_cluster(BAR(B_PEER), sc);
            WG_WAIT(0);
            reg_fence<56>(ac);
            PROFC(24);
            uint32_t rdst, rbar;
            asm volatile("mapa.shared::cluster.u32 %0, %1, %2;" : "=r"(rdst) : "r"(sb + OFF_Y + (5 + w) * 16384 + t * 16), "r"(kh ^ 1 ^ sc));
            asm volatile("mapa.shared::cluster.u32 %0, %1, %2;" : "=r"(rbar) : "r"(BAR(B_XCH + w)), "r"(kh ^ 1 ^ sc));
#define ACG(g, i) ac[4 * (g) + (i)]
#pragma unroll
            for (int g = 0; g < 7; g++) {
                const float v0 = kh ? ACG(g, 0) : ACG(g + 7, 0), v1 = kh ? ACG(g, 1) : ACG(g + 7, 1);
                const float v2 = kh ? ACG(g, 2) : ACG(g + 7, 2), v3 = kh ? ACG(g, 3) : ACG(g + 7, 3);
                if (!sc) asm volatile("st.async.shared::cluster.mbarrier::complete_tx::bytes.v4.f32 [%0], {%1,%2,%3,%4}, [%5];"
                             ::"r"(rdst + g * 2048), "f"(v0), "f"(v1), "f"(v2), "f"(v3), "r"(rbar) : "memory");
            }
            mbar_wait_cluster(BAR(B_XCH + w), sc);
            PROFC(25);
            bf16* og = (sc ? (bf16*)(g_h2 + 16 * 224 * 512) : p.out + (size_t)128 * r * DM) + (size_t)ra * DM + 56 * j + 2 * q;
#pragma unroll
            for (int g = 0; g < 7; g++) {
                const uint4 rv = *(const uint4*)(smem + OFF_Y + (5 + w) * 16384 + t * 16 + g * 2048);
                const float2 gb = *(const float2*)(smem + M_G + 224 + (8 * g + 2 * q) * 4);
                const float v0 = (kh ? ACG(g + 7, 0) : ACG(g, 0)) + __uint_as_float(rv.x), v1 = (kh ? ACG(g + 7, 1) : ACG(g, 1)) + __uint_as_float(rv.y);
                const float v2 = (kh ? ACG(g + 7, 2) : ACG(g, 2)) + __uint_as_float(rv.z), v3 = (kh ? ACG(g + 7, 3) : ACG(g, 3)) + __uint_as_float(rv.w);
                *(uint32_t*)(og + 8 * g) = pack2(fmaf(gb.x, v0, bf_lo(x1p[2 * g])), fmaf(gb.y, v1, bf_hi(x1p[2 * g])));
                *(uint32_t*)(og + 8 * DM + 8 * g) = pack2(fmaf(gb.x, v2, bf_lo(x1p[2 * g + 1])), fmaf(gb.y, v3, bf_hi(x1p[2 * g + 1])));
            }
        }
        PROFC(26);
        bar_sync(1 + w, 128);
        if (wi == 0) warp_arrive(BAR(B_DONE));
    } else {
        const int lane = fresh_tid() & 31;
        const bool early = kh == 0, gemv = r < 14;
        const int mcol = early ? 16 * (4 * r + nq) : 2 * DM + 32 * (4 * r + nq);
        const uint32_t wmbuf = sb + OFF_Y + HALF;
        asm volatile("setmaxnreg.dec.sync.aligned.u32 56;");
        if (warp == 9) {
#pragma unroll
            for (int i = 56; i < 64; i++) init_e(BAR(i), 1);
            fence_async_smem();
        }
        if (warp == 8) { init_e(BAR(B_WMFULL), 2); fence_async_smem(); }
        bar_arrive(0, 384);
        asm volatile("barrier.cluster.arrive.relaxed.aligned;" ::: "memory");
        uint32_t target = 0;
        if (warp == 8) {
            if (!sc) {
                expect_e(BAR(B_WMFULL), gemv ? 28672 >> early : 0);
                if (early && gemv) { tma3_e(wmbuf, &p.wm, mcol, 0, 0, BAR(B_WMFULL)); tma3_e(wmbuf + 7168, &p.wm, mcol, 224, 0, BAR(B_WMFULL)); }
#pragma unroll 1
                for (int kb = 0; kb < 7; kb++) {
                    expect_e(BAR(B_XFULL + kb), 16384);
                    tma3_e(sb + OFF_X + kb * 16384, &p.xm, 64 * kb, 128 * r, 0, BAR(B_XFULL + kb));
                }
            }
#pragma unroll 1
            for (int mt = 0; mt < 4; mt++) {
                if (mt == 1) {
                    if (!early && gemv) {
#pragma unroll 1
                        for (int k = 0; k < 4; k++) tma3_e(wmbuf + k * 7168, &p.wm, mcol + (k >> 1) * 16, (k & 1) * 224, 0, BAR(B_WMFULL));
                    }
                    bar_sync(9, 384);
                    if (sc) return;
                    mbar_wait(BAR(B_MOD1), 0);
                    mbar_wait(BAR(B_WMFREE), 0);
                }
                if (mt == 2) mbar_wait(BAR(B_XFREE), 0);
                if (mt == 3) mbar_wait(BAR(B_VRFULL), 0);
                const uint32_t bar = BAR(mt == 3 ? B_WOFULL : B_FULLK + mt), dst = sb + (mt < 2 ? OFF_Y : OFF_X) + (mt & 1) * HALF;
                const int c0 = (mt < 2 ? DM + DM * mt : 0) + 56 * j - 8 * kh;
                if (!sc) {
                    expect_e(bar, HALF);
                    tma3_e(dst, mt == 3 ? &p.wo : &p.qkv, c0, 0, 0, bar);
                    tma3_e(dst + HALF / 2, mt == 3 ? &p.wo : &p.qkv, c0, 224, 0, bar);
                }
            }
            expect_e(BAR(B_XCH), 14336);
            expect_e(BAR(B_XCH + 1), 14336);
        } else {
            if (warp == 10 && !sc) {
                l2_prefetch_e((const char*)p.wqkv + (size_t)b * 9408, 9408);
                if (lane == 0) sts1(sb + M_EPOCH, atomicAdd(&g_ticket, 1u) / NCTA);
            }
            if (warp == 11) {
#pragma unroll
                for (int i = 0; i < 8; i++) {
                    const int wd = lane + 32 * i;
                    const uint32_t cb = i < 7 ? __ldg((const uint32_t*)p.c + wd) : 0u;
                    sts1(wmbuf + 28672 + (wd >> 3) * 32 + (wd & 3) * 8 + (wd & 4), pack2(silu_bf(cb & 0xFFFFu), silu_bf(cb >> 16)));
                }
            }
            bar_sync(9, 384);
            if (sc) return;
            target = lds1(sb + M_EPOCH) + 1;
            const uint32_t tag = target & 0xFFFFu;
            if (warp == 11) {
                warp_arrive(BAR(B_WMFULL));
                mbar_wait(BAR(B_GEMV), 0);
                float sum = 0.f;
#pragma unroll
                for (int i = 0; i < 8; i++) sum += *(const float*)(smem + OFF_Y + HALF + 29696 + (i * 32 + (early ? lane & 15 : lane)) * 4);
                const uint32_t word = (pack2(sum, 0.f) << 16) | tag;
                if (gemv) {
                    uint32_t* mg = g_mod + mcol + (early ? (lane & 15) + (lane >> 4) * 4 * 6 * DM : lane);
#pragma unroll
                    for (int i = 0; i < 8; i++) if (i < 4 || !early) st_relaxed(mg + i * 6 * DM, word);
                }
                warp_arrive(BAR(B_WMFREE));
            }
            const uint4* modp = (const uint4*)g_mod + (r & 7) * (6 * DM / 4);
            const bool p2 = warp == 11;
            mbar_wait(BAR(p2 ? B_PUB : B_XFULL + 4), 0);
#pragma unroll 1
            for (int it = p2 ? 0 : warp - 9; it < (p2 ? 2 : warp - 8); it++) {
                const int i0 = lane + 32 * it, imax = p2 ? 251 : 223;
                uint4 v[4];
#pragma unroll 1
                for (int n = 0;; n++) {
                    uint32_t bad = 0;
#pragma unroll
                    for (int k = 0; k < 4; k++) {
                        const int i = min(i0 + 64 * k, imax);
                        v[k] = ld_relaxed4(modp + (i < 224 ? (p2 ? 336 : 0) + i : (i < 238 ? 14 * j + i : 14 * j + i + 322)));
                        bad |= (v[k].x ^ tag) | (v[k].y ^ tag) | (v[k].z ^ tag) | (v[k].w ^ tag);
                    }
                    if (!__any_sync(~0u, bad & 0xFFFFu)) break;
                    if (n > SPIN_LIMIT) __trap();
                }
#pragma unroll
                for (int k = 0; k < 4; k++) {
                    const int i = min(i0 + 64 * k, imax);
                    if (i < 224) {
                        const int isc = i >= 112, c4 = i - 112 * isc;
                        const float one = isc ? 1.f : 0.f;
                        const uint32_t a = sb + M_ST + (c4 >> 2) * 64 + (c4 & 1) * 32 + (c4 & 2) * 4 + (isc ? 0 : 4);
                        sts1(a, pack2(bf_hi(v[k].x) + one, bf_hi(v[k].y) + one));
                        sts1(a + 16, pack2(bf_hi(v[k].z) + one, bf_hi(v[k].w) + one));
                    } else {
                        sts4(sb + M_G + (i - 224) * 16, make_uint4(v[k].x & 0xFFFF0000u, v[k].y & 0xFFFF0000u, v[k].z & 0xFFFF0000u, v[k].w & 0xFFFF0000u));
                    }
                }
                warp_arrive(BAR(p2 ? B_MOD2 : B_MOD1));
            }
            if (warp == 9) {
#pragma unroll 1
                for (int kv = 0; kv < 2; kv++) {
                    mbar_wait(BAR(B_PUB + kv), 0);
                    wait_flags(g_flag + b * 128 + lane, target, (r >= 2 ? 6u : r == 1 ? 2u : 0u) << (8 * kv));
                    fence_async_global();
                    const uint32_t dst = sb + OFF_Y + (kv ? Y_VR : Y_K);
                    expect_e(BAR(B_KRFULL + kv), r >= 2 ? 28672 : r == 1 ? 14336 : 0);
                    if (r >= 2) bulk_e(dst, g_kv + (size_t)((b - 16) * 2 + kv) * 3584, 14336, BAR(B_KRFULL + kv));
                    if (r >= 1) bulk_e(dst + 14336, g_kv + (size_t)((b - 8) * 2 + kv) * 3584, 14336, BAR(B_KRFULL + kv));
                }
            } else if (warp == 11) {
                mbar_wait(BAR(B_VRFULL), 0);
                l2_prefetch_e((const char*)p.wg + (size_t)b * 12544, 12544);
                l2_prefetch_e((const char*)p.wu + (size_t)b * 12544, 12544);
#pragma unroll 1
                for (int k = 0; k < (r < 12 ? 2 : 1); k++) {
                    const int u = 28 * kh + r + 16 * k;
                    expect_e(BAR(B_XFULL + k), 7168);
                    tma3_e(sb + OFF_Y + 102400, &p.dn, 0, 32 * u, 14 * nq, BAR(B_XFULL + k));
                    mbar_wait(BAR(B_XFULL + k), 1);
                    asm volatile("{\n.reg .pred p;\nelect.sync _|p, 0xffffffff;\n@p cp.async.bulk.global.shared::cta.bulk_group [%0], [%1], 7168;\n"
                                 "cp.async.bulk.commit_group;\ncp.async.bulk.wait_group 0;\n}" ::"l"(g_wd + (size_t)(u * 4 + nq) * 1792), "r"(sb + OFF_Y + 102400) : "memory");
                    __syncwarp();
                }
                fence_gpu();
                if (lane < 16) st_relaxed(g_flag + (8 * lane + j) * 128 + 96 + r, target);
            }
        }
        if (warp == 8 || warp == 11) {
            const int sec = warp == 11;
            if (sec) ring_loader<1>(p, sb, r, j, lane); else ring_loader<0>(p, sb, r, j, lane);
            mbar_wait(BAR(B_DONE), 0);
        } else if (warp == 9) {
#pragma unroll
            for (int ev = 0; ev < 4; ev++) expect_e(BAR(B_GFULL + ev), ev < 2 ? HALF : HALF + 4096);
            mbar_wait(BAR(B_PUB + 2), 0);
            const uint32_t* fp = g_flag + b * 128 + 32 + lane;
            const uint32_t* src = g_ox + (size_t)2 * r * 14336;
            const float2* ssrc = g_st + 2 * r * 512;
#pragma unroll 1
            for (int n = 0, ev = 0; ev < 4; n++) {
                if (ev == 1) mbar_wait(BAR(B_PUB + 3), 0);
                uint32_t ok = __ballot_sync(~0u, (int)(ld_relaxed(fp) - target) >= 0) >> (8 * ev);
                while ((ok & 0xFFu) == 0xFFu) {
                    asm volatile("fence.acquire.gpu;" ::: "memory");
                    fence_async_global();
                    const uint32_t bar = BAR(B_GFULL + ev);
                    bulk_e(sb + (ev == 0 ? OFF_X : OFF_Y + (ev & 1) * HALF), src + (ev >> 1) * (34 * 14336) + (ev & 1) * 14336, HALF, bar);
                    if (ev >= 2) bulk_e(sb + OFF_X + X_STAT + (ev & 1) * 4096, ssrc + (ev & 1) * 512, 4096, bar);
                    if (ev) PROFH(4 + ev);
                    ev++; ok >>= 8;
                }
                if (n > SPIN_LIMIT) __trap();
            }
#pragma unroll 1
            for (int ps = 0; ps < 3; ps++) {
                mbar_wait(BAR(B_PUB + 6 + ps), 0);
                wait_flags(g_flag + b * 128 + 64 + lane, target, (0x55u << kh) << (8 * ps));
                warp_arrive(BAR(B_HRDY + ps));
                PROFH(9 + ps);
            }
        } else {
#pragma unroll 1
            for (int k = 0; k < 9; k++) {
                uint32_t* fp = k < 2 ? g_flag + (b + 8 * lane) * 128 + k * 8 + lane : g_flag + (8 * r + lane) * 128 + 16 + k * 8 + j;
                mbar_wait(BAR(B_PUB + k), 0);
                fence_gpu();
                if (k < 2 ? (lane == 1 || lane == 2) : lane < 8) st_relaxed(fp, target);
                if (k >= 3 && k <= 5) PROFH(k - 3);
            }
        }
    }
}

typedef CUresult (*EncodeFn)(CUtensorMap*, CUtensorMapDataType, cuuint32_t, void*, const cuuint64_t*, const cuuint64_t*, const cuuint32_t*,
                             const cuuint32_t*, CUtensorMapInterleave, CUtensorMapSwizzle, CUtensorMapL2promotion, CUtensorMapFloatOOBfill);

static void make_map(EncodeFn fn, CUtensorMap* m, const void* ptr, uint64_t d0, uint64_t d1, uint64_t d2, uint64_t s1, uint64_t s2,
                     uint32_t b0, uint32_t b1, uint32_t b2, CUtensorMapSwizzle sw) {
    cuuint64_t dims[3] = {d0, d1, d2}, strides[2] = {s1, s2};
    cuuint32_t box[3] = {b0, b1, b2}, es[3] = {1, 1, 1};
    CUresult rc = fn(m, CU_TENSOR_MAP_DATA_TYPE_BFLOAT16, 3, (void*)ptr, dims, strides, box, es, CU_TENSOR_MAP_INTERLEAVE_NONE, sw,
                     CU_TENSOR_MAP_L2_PROMOTION_L2_128B, CU_TENSOR_MAP_FLOAT_OOB_FILL_NONE);
    (void)rc;
}

extern "C" void kernel_launch(void* const* d_in, const int* in_sizes, int n_in, void* d_out, int out_size) {
    (void)in_sizes; (void)n_in; (void)out_size;
    static EncodeFn fn = nullptr;
    if (!fn) {
        cudaDriverEntryPointQueryResult st;
        cudaGetDriverEntryPoint("cuTensorMapEncodeTiled", (void**)&fn, cudaEnableDefault, &st);
        cudaFuncSetAttribute(fused_block_kernel, cudaFuncAttributeMaxDynamicSharedMemorySize, SMEM_BYTES);
    }
    Params p;
    p.x = (const bf16*)d_in[0];
    const bf16* wqkv = (const bf16*)d_in[1];
    p.wqkv = wqkv;
    p.wop = (const bf16*)d_in[2];
    p.wg = (const bf16*)d_in[4];
    p.wu = (const bf16*)d_in[5];
    p.wd = (const bf16*)d_in[6];
    p.c = (const bf16*)d_in[7];
    p.wmod = (const bf16*)d_in[8];
    p.out = (bf16*)d_out;
    p.zero = 0;
    make_map(fn, &p.wm, p.wmod, 2688, 448, 1, 5376, 5376 * 448, 16, 224, 1, CU_TENSOR_MAP_SWIZZLE_NONE);
    make_map(fn, &p.xm, p.x, 448, 2048, 1, 896, 896 * 2048, 64, 128, 1, CU_TENSOR_MAP_SWIZZLE_128B);
    make_map(fn, &p.qkv, wqkv, 1344, 448, 1, 2688, 2688 * 448, 64, 224, 1, CU_TENSOR_MAP_SWIZZLE_128B);
    make_map(fn, &p.wo, p.wop, 448, 448, 1, 896, 896 * 448, 64, 224, 1, CU_TENSOR_MAP_SWIZZLE_128B);
    make_map(fn, &p.ga, p.wg, 64, 448, 28, 3584, 128, 64, 32, 2, CU_TENSOR_MAP_SWIZZLE_128B);
    make_map(fn, &p.ua, p.wu, 64, 448, 28, 3584, 128, 64, 32, 2, CU_TENSOR_MAP_SWIZZLE_128B);
    make_map(fn, &p.gb, p.wg, 64, 448, 28, 3584, 128, 64, 64, 1, CU_TENSOR_MAP_SWIZZLE_128B);
    make_map(fn, &p.ub, p.wu, 64, 448, 28, 3584, 128, 64, 64, 1, CU_TENSOR_MAP_SWIZZLE_128B);
    make_map(fn, &p.gc, p.wg, 32, 448, 56, 3584, 64, 32, 64, 1, CU_TENSOR_MAP_SWIZZLE_64B);
    make_map(fn, &p.uc, p.wu, 32, 448, 56, 3584, 64, 32, 64, 1, CU_TENSOR_MAP_SWIZZLE_64B);
    make_map(fn, &p.dn, p.wd, 8, 1792, 56, 896, 16, 8, 32, 14, CU_TENSOR_MAP_SWIZZLE_NONE);
    fused_block_kernel<<<GRID, 384, SMEM_BYTES>>>(p);
}
```

```cpp
#include <cuda_runtime.h>
#include <cuda_bf16.h>
#include <cuda.h>
#include <stdint.h>

typedef __nv_bfloat16 bf16;

template<uint64_t CB> __device__ __forceinline__ void wgmma_rs_56(float* d, uint32_t a0, uint32_t a1, uint32_t a2, uint32_t a3, uint32_t db, int sd) {
  asm volatile("{\n.reg .pred p;\n.reg .b64 b;\nsetp.ne.b32 p, %33, 0;\nmov.b64 b, {%32, %34};\n"
    "wgmma.mma_async.sync.aligned.m64n56k16.f32.bf16.bf16 {%0,%1,%2,%3,%4,%5,%6,%7,%8,%9,%10,%11,%12,%13,%14,%15,%16,%17,%18,%19,%20,%21,%22,%23,%24,%25,%26,%27}, {%28,%29,%30,%31}, b, p, 1, 1, 1;\n}\n"
    : "+f"(d[0]),"+f"(d[1]),"+f"(d[2]),"+f"(d[3]),"+f"(d[4]),"+f"(d[5]),"+f"(d[6]),"+f"(d[7]),"+f"(d[8]),"+f"(d[9]),"+f"(d[10]),"+f"(d[11]),"+f"(d[12]),"+f"(d[13]),"+f"(d[14]),"+f"(d[15]),"+f"(d[16]),"+f"(d[17]),"+f"(d[18]),"+f"(d[19]),"+f"(d[20]),"+f"(d[21]),"+f"(d[22]),"+f"(d[23]),"+f"(d[24]),"+f"(d[25]),"+f"(d[26]),"+f"(d[27])
    : "r"(a0), "r"(a1), "r"(a2), "r"(a3), "r"(db), "r"(sd), "n"((uint32_t)(CB >> 32)));
}
template<uint64_t CA, uint64_t CB> __device__ __forceinline__ void wgmma_ss_56(float* d, uint32_t da, uint32_t db, int sd) {
  asm volatile("{\n.reg .pred p;\n.reg .b64 a, b;\nsetp.ne.b32 p, %30, 0;\nmov.b64 a, {%28, %31};\nmov.b64 b, {%29, %32};\n"
    "wgmma.mma_async.sync.aligned.m64n56k16.f32.bf16.bf16 {%0,%1,%2,%3,%4,%5,%6,%7,%8,%9,%10,%11,%12,%13,%14,%15,%16,%17,%18,%19,%20,%21,%22,%23,%24,%25,%26,%27}, a, b, p, 1, 1, 0, 1;\n}\n"
    : "+f"(d[0]),"+f"(d[1]),"+f"(d[2]),"+f"(d[3]),"+f"(d[4]),"+f"(d[5]),"+f"(d[6]),"+f"(d[7]),"+f"(d[8]),"+f"(d[9]),"+f"(d[10]),"+f"(d[11]),"+f"(d[12]),"+f"(d[13]),"+f"(d[14]),"+f"(d[15]),"+f"(d[16]),"+f"(d[17]),"+f"(d[18]),"+f"(d[19]),"+f"(d[20]),"+f"(d[21]),"+f"(d[22]),"+f"(d[23]),"+f"(d[24]),"+f"(d[25]),"+f"(d[26]),"+f"(d[27])
    : "r"(da), "r"(db), "r"(sd), "n"((uint32_t)(CA >> 32)), "n"((uint32_t)(CB >> 32)));
}
template<uint64_t CB> __device__ __forceinline__ void wgmma_rs_256(float* d, uint32_t a0, uint32_t a1, uint32_t a2, uint32_t a3, uint32_t db, int sd) {
  asm volatile("{\n.reg .pred p;\n.reg .b64 b;\nsetp.ne.b32 p, %133, 0;\nmov.b64 b, {%132, %134};\n"
    "wgmma.mma_async.sync.aligned.m64n256k16.f32.bf16.bf16 {%0,%1,%2,%3,%4,%5,%6,%7,%8,%9,%10,%11,%12,%13,%14,%15,%16,%17,%18,%19,%20,%21,%22,%23,%24,%25,%26,%27,%28,%29,%30,%31,%32,%33,%34,%35,%36,%37,%38,%39,%40,%41,%42,%43,%44,%45,%46,%47,%48,%49,%50,%51,%52,%53,%54,%55,%56,%57,%58,%59,%60,%61,%62,%63,%64,%65,%66,%67,%68,%69,%70,%71,%72,%73,%74,%75,%76,%77,%78,%79,%80,%81,%82,%83,%84,%85,%86,%87,%88,%89,%90,%91,%92,%93,%94,%95,%96,%97,%98,%99,%100,%101,%102,%103,%104,%105,%106,%107,%108,%109,%110,%111,%112,%113,%114,%115,%116,%117,%118,%119,%120,%121,%122,%123,%124,%125,%126,%127}, {%128,%129,%130,%131}, b, p, 1, 1, 1;\n}\n"
    : "+f"(d[0]),"+f"(d[1]),"+f"(d[2]),"+f"(d[3]),"+f"(d[4]),"+f"(d[5]),"+f"(d[6]),"+f"(d[7]),"+f"(d[8]),"+f"(d[9]),"+f"(d[10]),"+f"(d[11]),"+f"(d[12]),"+f"(d[13]),"+f"(d[14]),"+f"(d[15]),"+f"(d[16]),"+f"(d[17]),"+f"(d[18]),"+f"(d[19]),"+f"(d[20]),"+f"(d[21]),"+f"(d[22]),"+f"(d[23]),"+f"(d[24]),"+f"(d[25]),"+f"(d[26]),"+f"(d[27]),"+f"(d[28]),"+f"(d[29]),"+f"(d[30]),"+f"(d[31]),"+f"(d[32]),"+f"(d[33]),"+f"(d[34]),"+f"(d[35]),"+f"(d[36]),"+f"(d[37]),"+f"(d[38]),"+f"(d[39]),"+f"(d[40]),"+f"(d[41]),"+f"(d[42]),"+f"(d[43]),"+f"(d[44]),"+f"(d[45]),"+f"(d[46]),"+f"(d[47]),"+f"(d[48]),"+f"(d[49]),"+f"(d[50]),"+f"(d[51]),"+f"(d[52]),"+f"(d[53]),"+f"(d[54]),"+f"(d[55]),"+f"(d[56]),"+f"(d[57]),"+f"(d[58]),"+f"(d[59]),"+f"(d[60]),"+f"(d[61]),"+f"(d[62]),"+f"(d[63]),"+f"(d[64]),"+f"(d[65]),"+f"(d[66]),"+f"(d[67]),"+f"(d[68]),"+f"(d[69]),"+f"(d[70]),"+f"(d[71]),"+f"(d[72]),"+f"(d[73]),"+f"(d[74]),"+f"(d[75]),"+f"(d[76]),"+f"(d[77]),"+f"(d[78]),"+f"(d[79]),"+f"(d[80]),"+f"(d[81]),"+f"(d[82]),"+f"(d[83]),"+f"(d[84]),"+f"(d[85]),"+f"(d[86]),"+f"(d[87]),"+f"(d[88]),"+f"(d[89]),"+f"(d[90]),"+f"(d[91]),"+f"(d[92]),"+f"(d[93]),"+f"(d[94]),"+f"(d[95]),"+f"(d[96]),"+f"(d[97]),"+f"(d[98]),"+f"(d[99]),"+f"(d[100]),"+f"(d[101]),"+f"(d[102]),"+f"(d[103]),"+f"(d[104]),"+f"(d[105]),"+f"(d[106]),"+f"(d[107]),"+f"(d[108]),"+f"(d[109]),"+f"(d[110]),"+f"(d[111]),"+f"(d[112]),"+f"(d[113]),"+f"(d[114]),"+f"(d[115]),"+f"(d[116]),"+f"(d[117]),"+f"(d[118]),"+f"(d[119]),"+f"(d[120]),"+f"(d[121]),"+f"(d[122]),"+f"(d[123]),"+f"(d[124]),"+f"(d[125]),"+f"(d[126]),"+f"(d[127])
    : "r"(a0), "r"(a1), "r"(a2), "r"(a3), "r"(db), "r"(sd), "n"((uint32_t)(CB >> 32)));
}
template<uint64_t CA, uint64_t CB> __device__ __forceinline__ void wgmma_ss_128(float* d, uint32_t da, uint32_t db, int sd) {
  asm volatile("{\n.reg .pred p;\n.reg .b64 a, b;\nsetp.ne.b32 p, %66, 0;\nmov.b64 a, {%64, %67};\nmov.b64 b, {%65, %68};\n"
    "wgmma.mma_async.sync.aligned.m64n128k16.f32.bf16.bf16 {%0,%1,%2,%3,%4,%5,%6,%7,%8,%9,%10,%11,%12,%13,%14,%15,%16,%17,%18,%19,%20,%21,%22,%23,%24,%25,%26,%27,%28,%29,%30,%31,%32,%33,%34,%35,%36,%37,%38,%39,%40,%41,%42,%43,%44,%45,%46,%47,%48,%49,%50,%51,%52,%53,%54,%55,%56,%57,%58,%59,%60,%61,%62,%63}, a, b, p, 1, 1, 0, 1;\n}\n"
    : "+f"(d[0]),"+f"(d[1]),"+f"(d[2]),"+f"(d[3]),"+f"(d[4]),"+f"(d[5]),"+f"(d[6]),"+f"(d[7]),"+f"(d[8]),"+f"(d[9]),"+f"(d[10]),"+f"(d[11]),"+f"(d[12]),"+f"(d[13]),"+f"(d[14]),"+f"(d[15]),"+f"(d[16]),"+f"(d[17]),"+f"(d[18]),"+f"(d[19]),"+f"(d[20]),"+f"(d[21]),"+f"(d[22]),"+f"(d[23]),"+f"(d[24]),"+f"(d[25]),"+f"(d[26]),"+f"(d[27]),"+f"(d[28]),"+f"(d[29]),"+f"(d[30]),"+f"(d[31]),"+f"(d[32]),"+f"(d[33]),"+f"(d[34]),"+f"(d[35]),"+f"(d[36]),"+f"(d[37]),"+f"(d[38]),"+f"(d[39]),"+f"(d[40]),"+f"(d[41]),"+f"(d[42]),"+f"(d[43]),"+f"(d[44]),"+f"(d[45]),"+f"(d[46]),"+f"(d[47]),"+f"(d[48]),"+f"(d[49]),"+f"(d[50]),"+f"(d[51]),"+f"(d[52]),"+f"(d[53]),"+f"(d[54]),"+f"(d[55]),"+f"(d[56]),"+f"(d[57]),"+f"(d[58]),"+f"(d[59]),"+f"(d[60]),"+f"(d[61]),"+f"(d[62]),"+f"(d[63])
    : "r"(da), "r"(db), "r"(sd), "n"((uint32_t)(CA >> 32)), "n"((uint32_t)(CB >> 32)));
}
template<uint64_t CA, uint64_t CB> __device__ __forceinline__ void wgmma_ss_64(float* d, uint32_t da, uint32_t db, int sd) {
  asm volatile("{\n.reg .pred p;\n.reg .b64 a, b;\nsetp.ne.b32 p, %34, 0;\nmov.b64 a, {%32, %35};\nmov.b64 b, {%33, %36};\n"
    "wgmma.mma_async.sync.aligned.m64n64k16.f32.bf16.bf16 {%0,%1,%2,%3,%4,%5,%6,%7,%8,%9,%10,%11,%12,%13,%14,%15,%16,%17,%18,%19,%20,%21,%22,%23,%24,%25,%26,%27,%28,%29,%30,%31}, a, b, p, 1, 1, 0, 1;\n}\n"
    : "+f"(d[0]),"+f"(d[1]),"+f"(d[2]),"+f"(d[3]),"+f"(d[4]),"+f"(d[5]),"+f"(d[6]),"+f"(d[7]),"+f"(d[8]),"+f"(d[9]),"+f"(d[10]),"+f"(d[11]),"+f"(d[12]),"+f"(d[13]),"+f"(d[14]),"+f"(d[15]),"+f"(d[16]),"+f"(d[17]),"+f"(d[18]),"+f"(d[19]),"+f"(d[20]),"+f"(d[21]),"+f"(d[22]),"+f"(d[23]),"+f"(d[24]),"+f"(d[25]),"+f"(d[26]),"+f"(d[27]),"+f"(d[28]),"+f"(d[29]),"+f"(d[30]),"+f"(d[31])
    : "r"(da), "r"(db), "r"(sd), "n"((uint32_t)(CA >> 32)), "n"((uint32_t)(CB >> 32)));
}
template<uint64_t CA, uint64_t CB> __device__ __forceinline__ void wgmma_ss_112(float* d, uint32_t da, uint32_t db, int sd) {
  asm volatile("{\n.reg .pred p;\n.reg .b64 a, b;\nsetp.ne.b32 p, %58, 0;\nmov.b64 a, {%56, %59};\nmov.b64 b, {%57, %60};\n"
    "wgmma.mma_async.sync.aligned.m64n112k16.f32.bf16.bf16 {%0,%1,%2,%3,%4,%5,%6,%7,%8,%9,%10,%11,%12,%13,%14,%15,%16,%17,%18,%19,%20,%21,%22,%23,%24,%25,%26,%27,%28,%29,%30,%31,%32,%33,%34,%35,%36,%37,%38,%39,%40,%41,%42,%43,%44,%45,%46,%47,%48,%49,%50,%51,%52,%53,%54,%55}, a, b, p, 1, 1, 0, 1;\n}\n"
    : "+f"(d[0]),"+f"(d[1]),"+f"(d[2]),"+f"(d[3]),"+f"(d[4]),"+f"(d[5]),"+f"(d[6]),"+f"(d[7]),"+f"(d[8]),"+f"(d[9]),"+f"(d[10]),"+f"(d[11]),"+f"(d[12]),"+f"(d[13]),"+f"(d[14]),"+f"(d[15]),"+f"(d[16]),"+f"(d[17]),"+f"(d[18]),"+f"(d[19]),"+f"(d[20]),"+f"(d[21]),"+f"(d[22]),"+f"(d[23]),"+f"(d[24]),"+f"(d[25]),"+f"(d[26]),"+f"(d[27]),"+f"(d[28]),"+f"(d[29]),"+f"(d[30]),"+f"(d[31]),"+f"(d[32]),"+f"(d[33]),"+f"(d[34]),"+f"(d[35]),"+f"(d[36]),"+f"(d[37]),"+f"(d[38]),"+f"(d[39]),"+f"(d[40]),"+f"(d[41]),"+f"(d[42]),"+f"(d[43]),"+f"(d[44]),"+f"(d[45]),"+f"(d[46]),"+f"(d[47]),"+f"(d[48]),"+f"(d[49]),"+f"(d[50]),"+f"(d[51]),"+f"(d[52]),"+f"(d[53]),"+f"(d[54]),"+f"(d[55])
    : "r"(da), "r"(db), "r"(sd), "n"((uint32_t)(CA >> 32)), "n"((uint32_t)(CB >> 32)));
}
template<uint64_t CB> __device__ __forceinline__ void wgmma_rs_112(float* d, uint32_t a0, uint32_t a1, uint32_t a2, uint32_t a3, uint32_t db, int sd) {
  asm volatile("{\n.reg .pred p;\n.reg .b64 b;\nsetp.ne.b32 p, %61, 0;\nmov.b64 b, {%60, %62};\n"
    "wgmma.mma_async.sync.aligned.m64n112k16.f32.bf16.bf16 {%0,%1,%2,%3,%4,%5,%6,%7,%8,%9,%10,%11,%12,%13,%14,%15,%16,%17,%18,%19,%20,%21,%22,%23,%24,%25,%26,%27,%28,%29,%30,%31,%32,%33,%34,%35,%36,%37,%38,%39,%40,%41,%42,%43,%44,%45,%46,%47,%48,%49,%50,%51,%52,%53,%54,%55}, {%56,%57,%58,%59}, b, p, 1, 1, 1;\n}\n"
    : "+f"(d[0]),"+f"(d[1]),"+f"(d[2]),"+f"(d[3]),"+f"(d[4]),"+f"(d[5]),"+f"(d[6]),"+f"(d[7]),"+f"(d[8]),"+f"(d[9]),"+f"(d[10]),"+f"(d[11]),"+f"(d[12]),"+f"(d[13]),"+f"(d[14]),"+f"(d[15]),"+f"(d[16]),"+f"(d[17]),"+f"(d[18]),"+f"(d[19]),"+f"(d[20]),"+f"(d[21]),"+f"(d[22]),"+f"(d[23]),"+f"(d[24]),"+f"(d[25]),"+f"(d[26]),"+f"(d[27]),"+f"(d[28]),"+f"(d[29]),"+f"(d[30]),"+f"(d[31]),"+f"(d[32]),"+f"(d[33]),"+f"(d[34]),"+f"(d[35]),"+f"(d[36]),"+f"(d[37]),"+f"(d[38]),"+f"(d[39]),"+f"(d[40]),"+f"(d[41]),"+f"(d[42]),"+f"(d[43]),"+f"(d[44]),"+f"(d[45]),"+f"(d[46]),"+f"(d[47]),"+f"(d[48]),"+f"(d[49]),"+f"(d[50]),"+f"(d[51]),"+f"(d[52]),"+f"(d[53]),"+f"(d[54]),"+f"(d[55])
    : "r"(a0), "r"(a1), "r"(a2), "r"(a3), "r"(db), "r"(sd), "n"((uint32_t)(CB >> 32)));
}

constexpr int DM = 448;
constexpr int NCTA = 128;
#define MAPPING 1
#define GRID 132
#define PINGPONG 0
#define WIN 6
#define WIN_END 25
#define UNR_G2 21
#define UNR_B 7
#define UNR_C 7
constexpr int kG2 = UNR_G2, kB = UNR_B, kC = UNR_C;
#define MAP_S 4
constexpr int SPIN_LIMIT = 1 << 22;

constexpr uint32_t OFF_X = 0, OFF_Y = 114688, OFF_MISC = 229376, SMEM_BYTES = 232448;
constexpr uint32_t Y_VR = 0, Y_K = 28672, Y_KOWN = 57344, Y_VOWN = 71680, Y_Q = 86016;
constexpr uint32_t HALF = 57344;
constexpr uint32_t M_BAR = OFF_MISC;
constexpr uint32_t M_ST = OFF_MISC + 512;
constexpr uint32_t M_G = OFF_MISC + 2304;
constexpr uint32_t M_EPOCH = OFF_MISC + 3040;
enum { B_XFULL = 0, B_FULLK = 7, B_FULLV = 8, B_FULLQ, B_KRFULL, B_VRFULL, B_WOFULL, B_XCH, B_FULL = 16, B_MOD1 = 28, B_MOD2, B_WMFULL,
       B_EMPTY = 32, B_XFREE = B_EMPTY + 12, B_GEMV, B_PEER,
       B_PUB = 47,
       B_WMFREE = 56, B_HRDY, B_GFULL = B_HRDY + 3, B_DONE = 31 };
constexpr uint32_t X_STAT = 49152;

__device__ uint32_t g_ticket;
__device__ __align__(128) uint32_t g_mod[8 * 6 * DM];
__device__ __align__(128) uint32_t g_flag[144 * 128];
__device__ __align__(128) uint32_t g_kv[17 * 8 * 2 * 3584];
__device__ __align__(128) uint32_t g_ox[3 * 34 * 14336];
#define g_o g_ox
#define g_x1 (g_ox + 34 * 14336)
__device__ __align__(128) float2 g_st[2 * 34 * 8 * 64];
__device__ __align__(128) uint32_t g_wd[56 * 4 * 1792];
__device__ __align__(128) uint32_t g_h2[17 * 224 * 512];
#define PROFH(id)
#define PROFH1(id)
#define PROFC(id)

struct alignas(64) Params {
    CUtensorMap wm, xm, qkv, wo, ga, ua, gb, ub, gc, uc, dn;
    const bf16 *x, *c, *wqkv, *wmod, *wg, *wu, *wd, *wop;
    bf16* out;
    uint32_t zero;
};

__device__ __forceinline__ void mbar_init(uint32_t bar, int cnt) { asm volatile("mbarrier.init.shared::cta.b64 [%0], %1;" ::"r"(bar), "r"(cnt) : "memory"); }
__device__ __forceinline__ void mbar_expect_tx(uint32_t bar, uint32_t bytes) { asm volatile("mbarrier.arrive.expect_tx.shared::cta.b64 _, [%0], %1;" ::"r"(bar), "r"(bytes) : "memory"); }
__device__ __forceinline__ void mbar_arrive(uint32_t bar) { asm volatile("mbarrier.arrive.shared::cta.b64 _, [%0];" ::"r"(bar) : "memory"); }
__device__ __forceinline__ void mbar_wait(uint32_t bar, uint32_t parity) {
    uint32_t ok; int n = 0;
    do {
        asm volatile("{\n.reg .pred p;\nmbarrier.try_wait.parity.shared::cta.b64 p, [%1], %2;\nselp.u32 %0, 1, 0, p;\n}" : "=r"(ok) : "r"(bar), "r"(parity) : "memory");
        if (++n > SPIN_LIMIT) __trap();
    } while (!ok);
}
__device__ __forceinline__ void mbar_wait_c(uint32_t bar, uint32_t parity) {
    asm volatile("{\n.reg .pred p;\nWL:\nmbarrier.try_wait.parity.shared::cta.b64 p, [%0], %1;\n@!p bra WL;\n}" ::"r"(bar), "r"(parity) : "memory");
}
__device__ __forceinline__ void mbar_wait_cluster(uint32_t bar, uint32_t parity) {
    uint32_t ok; int n = 0;
    do {
        asm volatile("{\n.reg .pred p;\nmbarrier.try_wait.parity.acquire.cluster.shared::cta.b64 p, [%1], %2;\nselp.u32 %0, 1, 0, p;\n}" : "=r"(ok) : "r"(bar), "r"(parity) : "memory");
        if (++n > SPIN_LIMIT) __trap();
    } while (!ok);
}
__device__ __forceinline__ void warp_arrive(uint32_t bar) {
    __syncwarp();
    asm volatile("{\n.reg .pred p;\nelect.sync _|p, 0xffffffff;\n@p mbarrier.arrive.shared::cta.b64 _, [%0];\n}" ::"r"(bar) : "memory");
}
__device__ __forceinline__ int opaque(int v) { return __shfl_sync(~0u, v, 0); }
__device__ __forceinline__ int fresh_tid() { int v; asm volatile("mov.u32 %0, %%tid.x;" : "=r"(v)); return v; }
__device__ __forceinline__ void bar_sync(int id, int n) { asm volatile("bar.sync %0, %1;" ::"r"(id), "r"(n) : "memory"); }
__device__ __forceinline__ void bar_arrive(int id, int n) { asm volatile("bar.arrive %0, %1;" ::"r"(id), "r"(n) : "memory"); }
__device__ __forceinline__ void fence_async_smem() { asm volatile("fence.proxy.async.shared::cta;" ::: "memory"); }
__device__ __forceinline__ void fence_async_global() { asm volatile("fence.proxy.async.global;" ::: "memory"); }
__device__ __forceinline__ void fence_gpu() { asm volatile("fence.release.gpu;" ::: "memory"); }
__device__ __forceinline__ void tma3(uint32_t dst, const CUtensorMap* m, int c0, int c1, int c2, uint32_t bar) {
    asm volatile("cp.async.bulk.tensor.3d.shared::cluster.global.mbarrier::complete_tx::bytes [%0], [%1, {%3, %4, %5}], [%2];"
                 ::"r"(dst), "l"(m), "r"(bar), "r"(c0), "r"(c1), "r"(c2) : "memory");
}
__device__ __forceinline__ void bulk_load(uint32_t dst, const void* src, uint32_t bytes, uint32_t bar) {
    asm volatile("cp.async.bulk.shared::cluster.global.mbarrier::complete_tx::bytes [%0], [%1], %2, [%3];" ::"r"(dst), "l"(src), "r"(bytes), "r"(bar) : "memory");
}
__device__ __forceinline__ void expect_e(uint32_t bar, uint32_t bytes) {
    asm volatile("{\n.reg .pred p;\nelect.sync _|p, 0xffffffff;\n@p mbarrier.arrive.expect_tx.shared::cta.b64 _, [%0], %1;\n}" ::"r"(bar), "r"(bytes) : "memory");
}
__device__ __forceinline__ void tma3_e(uint32_t dst, const CUtensorMap* m, int c0, int c1, int c2, uint32_t bar) {
    asm volatile("{\n.reg .pred p;\nelect.sync _|p, 0xffffffff;\n@p cp.async.bulk.tensor.3d.shared::cluster.global.mbarrier::complete_tx::bytes [%0], [%1, {%3, %4, %5}], [%2];\n}"
                 ::"r"(dst), "l"(m), "r"(bar), "r"(c0), "r"(c1), "r"(c2) : "memory");
}
__device__ __forceinline__ void bulk_e(uint32_t dst, const void* src, uint32_t bytes, uint32_t bar) {
    asm volatile("{\n.reg .pred p;\nelect.sync _|p, 0xffffffff;\n@p cp.async.bulk.shared::cluster.global.mbarrier::complete_tx::bytes [%0], [%1], %2, [%3];\n}"
                 ::"r"(dst), "l"(src), "r"(bytes), "r"(bar) : "memory");
}
__device__ __forceinline__ void init_e(uint32_t bar, int cnt) {
    asm volatile("{\n.reg .pred p;\nelect.sync _|p, 0xffffffff;\n@p mbarrier.init.shared::cta.b64 [%0], %1;\n}" ::"r"(bar), "r"(cnt) : "memory");
}
__device__ __forceinline__ void l2_prefetch_e(const void* src, uint32_t bytes) {
    asm volatile("{\n.reg .pred p;\nelect.sync _|p, 0xffffffff;\n@p cp.async.bulk.prefetch.L2.global [%0], %1;\n}" ::"l"(src), "r"(bytes) : "memory");
}
__device__ __forceinline__ uint32_t ld_relaxed(const uint32_t* p) { uint32_t v; asm volatile("ld.relaxed.gpu.global.u32 %0, [%1];" : "=r"(v) : "l"(p) : "memory"); return v; }
__device__ __forceinline__ void st_relaxed(uint32_t* p, uint32_t v) { asm volatile("st.relaxed.gpu.global.u32 [%0], %1;" ::"l"(p), "r"(v) : "memory"); }
__device__ __forceinline__ uint4 ld_relaxed4(const uint4* p) { uint4 v; asm volatile("ld.relaxed.gpu.global.v4.u32 {%0,%1,%2,%3}, [%4];" : "=r"(v.x), "=r"(v.y), "=r"(v.z), "=r"(v.w) : "l"(p) : "memory"); return v; }
__device__ __forceinline__ void st_relaxed4(uint4* p, uint4 v) { asm volatile("st.relaxed.gpu.global.v4.u32 [%0], {%1,%2,%3,%4};" ::"l"(p), "r"(v.x), "r"(v.y), "r"(v.z), "r"(v.w) : "memory"); }
__device__ __forceinline__ uint4 ldg_nc4(const void* p) { uint4 v; asm volatile("ld.global.nc.L1::no_allocate.v4.u32 {%0,%1,%2,%3}, [%4];" : "=r"(v.x), "=r"(v.y), "=r"(v.z), "=r"(v.w) : "l"(p)); return v; }
__device__ __forceinline__ uint32_t ldg_nc(const void* p) { uint32_t v; asm volatile("ld.global.nc.u32 %0, [%1];" : "=r"(v) : "l"(p)); return v; }
__device__ __forceinline__ uint32_t ld_acquire(const uint32_t* p) { uint32_t v; asm volatile("ld.acquire.gpu.global.u32 %0, [%1];" : "=r"(v) : "l"(p) : "memory"); return v; }
__device__ __forceinline__ uint4 lds4(uint32_t a) { uint4 v; asm volatile("ld.shared.v4.u32 {%0,%1,%2,%3}, [%4];" : "=r"(v.x), "=r"(v.y), "=r"(v.z), "=r"(v.w) : "r"(a) : "memory"); return v; }
__device__ __forceinline__ float2 lds2f(uint32_t a) { float2 v; asm volatile("ld.shared.v2.f32 {%0,%1}, [%2];" : "=f"(v.x), "=f"(v.y) : "r"(a) : "memory"); return v; }
__device__ __forceinline__ uint32_t lds1(uint32_t a) { uint32_t v; asm volatile("ld.shared.u32 %0, [%1];" : "=r"(v) : "r"(a) : "memory"); return v; }
__device__ __forceinline__ void sts4(uint32_t a, uint4 v) { asm volatile("st.shared.v4.u32 [%0], {%1,%2,%3,%4};" ::"r"(a), "r"(v.x), "r"(v.y), "r"(v.z), "r"(v.w) : "memory"); }
__device__ __forceinline__ void sts2(uint32_t a, uint32_t x, uint32_t y) { asm volatile("st.shared.v2.u32 [%0], {%1,%2};" ::"r"(a), "r"(x), "r"(y) : "memory"); }
__device__ __forceinline__ void sts1(uint32_t a, uint32_t v) { asm volatile("st.shared.u32 [%0], %1;" ::"r"(a), "r"(v) : "memory"); }
__device__ __forceinline__ void stsm4(uint32_t a, uint32_t r0, uint32_t r1, uint32_t r2, uint32_t r3) {
    asm volatile("stmatrix.sync.aligned.m8n8.x4.shared.b16 [%0], {%1,%2,%3,%4};" ::"r"(a), "r"(r0), "r"(r1), "r"(r2), "r"(r3));
}
__device__ __forceinline__ uint32_t pack2(float lo, float hi) { uint32_t r; asm("cvt.rn.bf16x2.f32 %0, %1, %2;" : "=r"(r) : "f"(hi), "f"(lo)); return r; }
__device__ __forceinline__ uint32_t pack2_relu(float lo, float hi) { uint32_t r; asm("cvt.rn.relu.bf16x2.f32 %0, %1, %2;" : "=r"(r) : "f"(hi), "f"(lo)); return r; }
__device__ __forceinline__ uint32_t hfma2(uint32_t a, uint32_t b, uint32_t c) { uint32_t r; asm("fma.rn.bf16x2 %0, %1, %2, %3;" : "=r"(r) : "r"(a), "r"(b), "r"(c)); return r; }
__device__ __forceinline__ uint32_t hmul2(uint32_t a, uint32_t b) { uint32_t r; asm("mul.rn.bf16x2 %0, %1, %2;" : "=r"(r) : "r"(a), "r"(b)); return r; }
__device__ __forceinline__ float bf_lo(uint32_t v) { return __uint_as_float(v << 16); }
__device__ __forceinline__ float bf_hi(uint32_t v) { return __uint_as_float(v & 0xFFFF0000u); }
__device__ __forceinline__ float bf_round(float v) { return bf_lo(pack2(v, 0.f)); }
__device__ __forceinline__ float ex2(float x) { float r; asm("ex2.approx.ftz.f32 %0, %1;" : "=f"(r) : "f"(x)); return r; }
__device__ __forceinline__ void mma16816(float* d, uint32_t a0, uint32_t a1, uint32_t a2, uint32_t a3, uint32_t b0, uint32_t b1) {
    asm("mma.sync.aligned.m16n8k16.row.col.f32.bf16.bf16.f32 {%0,%1,%2,%3}, {%4,%5,%6,%7}, {%8,%9}, {%0,%1,%2,%3};"
        : "+f"(d[0]), "+f"(d[1]), "+f"(d[2]), "+f"(d[3]) : "r"(a0), "r"(a1), "r"(a2), "r"(a3), "r"(b0), "r"(b1));
}
__device__ __forceinline__ void mma16816_first(float* d, uint32_t a0, uint32_t a1, uint32_t a2, uint32_t a3, uint32_t b0, uint32_t b1) {
    asm volatile("mma.sync.aligned.m16n8k16.row.col.f32.bf16.bf16.f32 {%0,%1,%2,%3}, {%4,%5,%6,%7}, {%8,%9}, {%10,%10,%10,%10};"
        : "=f"(d[0]), "=f"(d[1]), "=f"(d[2]), "=f"(d[3]) : "r"(a0), "r"(a1), "r"(a2), "r"(a3), "r"(b0), "r"(b1), "f"(0.f));
}
__device__ __forceinline__ void mma16816_v(float* d, uint32_t a0, uint32_t a1, uint32_t a2, uint32_t a3, uint32_t b0, uint32_t b1) {
    asm volatile("mma.sync.aligned.m16n8k16.row.col.f32.bf16.bf16.f32 {%0,%1,%2,%3}, {%4,%5,%6,%7}, {%8,%9}, {%0,%1,%2,%3};"
        : "+f"(d[0]), "+f"(d[1]), "+f"(d[2]), "+f"(d[3]) : "r"(a0), "r"(a1), "r"(a2), "r"(a3), "r"(b0), "r"(b1));
}
__device__ __forceinline__ void mma1688(float* d, uint32_t a0, uint32_t a1, uint32_t b0) {
    asm("mma.sync.aligned.m16n8k8.row.col.f32.bf16.bf16.f32 {%0,%1,%2,%3}, {%4,%5}, {%6}, {%0,%1,%2,%3};"
        : "+f"(d[0]), "+f"(d[1]), "+f"(d[2]), "+f"(d[3]) : "r"(a0), "r"(a1), "r"(b0));
}
__device__ __forceinline__ void ldsm4(uint32_t a, uint32_t* r) {
    asm volatile("ldmatrix.sync.aligned.m8n8.x4.shared.b16 {%0,%1,%2,%3}, [%4];" : "=r"(r[0]), "=r"(r[1]), "=r"(r[2]), "=r"(r[3]) : "r"(a));
}
__device__ __forceinline__ void ldsm4t(uint32_t a, uint32_t* r) {
    asm volatile("ldmatrix.sync.aligned.m8n8.x4.trans.shared.b16 {%0,%1,%2,%3}, [%4];" : "=r"(r[0]), "=r"(r[1]), "=r"(r[2]), "=r"(r[3]) : "r"(a));
}
__device__ __forceinline__ float rcp(float x) { float r; asm("rcp.approx.ftz.f32 %0, %1;" : "=f"(r) : "f"(x)); return r; }
__device__ __forceinline__ uint2 ld_relaxed2(const void* p) { uint2 v; asm volatile("ld.relaxed.gpu.global.v2.u32 {%0,%1}, [%2];" : "=r"(v.x), "=r"(v.y) : "l"(p) : "memory"); return v; }
__device__ __forceinline__ void st_relaxed2(void* p, uint32_t x, uint32_t y) { asm volatile("st.relaxed.gpu.global.v2.u32 [%0], {%1,%2};" ::"l"(p), "r"(max(x, 1u)), "r"(max(y, 1u)) : "memory"); }
__host__ __device__ constexpr uint64_t dconst(uint32_t lbo, uint32_t sbo, uint32_t swz) {
    return ((uint64_t)(lbo >> 4) << 16) | ((uint64_t)(sbo >> 4) << 32) | ((uint64_t)swz << 62);
}
__device__ __forceinline__ uint32_t mkdesc(uint32_t addr, uint64_t c) { return (uint32_t)c | ((addr & 0x3FFFF) >> 4); }
#define WG_FENCE() asm volatile("wgmma.fence.sync.aligned;" ::: "memory")
#define WG_COMMIT() asm volatile("wgmma.commit_group.sync.aligned;" ::: "memory")
#define WG_WAIT(n) asm volatile("wgmma.wait_group.sync.aligned %0;" ::"n"(n) : "memory")
template <int N> __device__ __forceinline__ void reg_fence(float* d) {
#pragma unroll
    for (int i = 0; i < N; i++) asm volatile("" : "+f"(d[i])::"memory");
}
template <int N> __device__ __forceinline__ void reg_def(float* d) {
#pragma unroll
    for (int i = 0; i < N; i++) asm volatile("" : "=f"(d[i]));
}
template <int N> __device__ __forceinline__ void reg_def(uint32_t* d) {
#pragma unroll
    for (int i = 0; i < N; i++) asm volatile("" : "=r"(d[i]));
}
__device__ __forceinline__ bool is_unset(uint4 v) { return min(min(v.x, v.y), min(v.z, v.w)) == 0u; }
__device__ __forceinline__ uint4 nz4(uint32_t a, uint32_t b, uint32_t c, uint32_t d) { return make_uint4(max(a, 1u), max(b, 1u), max(c, 1u), max(d, 1u)); }
__device__ __forceinline__ void wait_flags(const uint32_t* p, uint32_t target, uint32_t mask) {
    int n = 0;
    while (~__ballot_sync(~0u, (int)(ld_relaxed(p) - target) >= 0) & mask) { if (++n > SPIN_LIMIT) __trap(); }
    asm volatile("fence.acquire.gpu;" ::: "memory");
}
__device__ __forceinline__ float silu_bf(uint32_t cbits) {
    const float c = __uint_as_float(cbits << 16);
    return bf_round(__fdividef(c, 1.f + fminf(ex2(-1.4426950408889634f * c), 1e30f)));
}
__device__ __forceinline__ void gemv_part(uint32_t wmbuf, int npanel, int wp, int lane) {
    const uint32_t wa = wmbuf + wp * 512 + (8 * (lane >> 4) + (lane & 7)) * 32 + ((lane >> 3) & 1) * 16;
    uint2 B[4];
#pragma unroll
    for (int i = 0; i < 4; i++) { const float2 v = lds2f(wmbuf + 28672 + (wp + 8 * i) * 32 + (lane & 3) * 8); B[i] = make_uint2(__float_as_uint(v.x), __float_as_uint(v.y)); }
#pragma unroll 1
    for (int pn = 0; pn < npanel; pn++) {
        float d[4] = {};
        uint32_t A[16];
#pragma unroll
        for (int i = 0; i < 4; i++) ldsm4t(wa + pn * 14336 + (i < 3 || wp < 4 ? i : 0) * 4096, A + 4 * i);
#pragma unroll
        for (int i = 0; i < 4; i++) mma16816(d, A[4 * i], A[4 * i + 1], A[4 * i + 2], A[4 * i + 3], B[i].x, B[i].y);
        if ((lane & 3) == 0) {
            sts1(wmbuf + 29696 + (wp * 32 + pn * 16 + (lane >> 2)) * 4, __float_as_uint(d[0]));
            sts1(wmbuf + 29696 + (wp * 32 + pn * 16 + 8 + (lane >> 2)) * 4, __float_as_uint(d[2]));
        }
    }
}
__device__ __forceinline__ int pass_f(int fs, int ps) { return 224 * fs + ((fs & 1) ? (ps == 0 ? 96 : ps == 1 ? 32 : 0) : (ps == 0 ? 0 : ps == 1 ? 128 : 192)); }
__device__ __forceinline__ constexpr uint32_t slot_off(int l) { return (l < 3 || l > 6 ? l : l == 6 ? 3 : l + 1) * 16384; }
__device__ __forceinline__ void ln_coeffs(float mean, float msq, uint32_t& r2, uint32_t& n2) {
    const float rs = bf_round(rsqrtf(fmaxf(msq - mean * mean, 0.f) + 1e-5f));
    r2 = pack2(rs, rs);
    n2 = pack2(-mean * rs, -mean * rs);
}

#define LOADW bulk_e(dst, g_wd + (size_t)((f >> 5) * 4 + nq) * 1792, 7168, bar);
template <int sec> __device__ __forceinline__ void ring_loader(const Params& p, uint32_t sb_, int r_, int j_, int lane) {
    const uint32_t sb = opaque(sb_);
    const int r = opaque(r_), j = opaque(j_), nq = j >> 1, fs = 4 * (j & 1) + nq;
    const int fa = pass_f(fs, 0), fb = pass_f(fs, 1), fc = pass_f(fs, 2);
#define BAR(i) (sb + M_BAR + 8 * (i))
#define kh (j & 1)
            int sl = 0;
            mbar_wait(BAR(B_PUB + 2), 0);
            wait_flags(g_flag + (8 * r + j) * 128 + 96 + lane, lds1(sb + M_EPOCH) + 1, 0xFFFFu);
            fence_async_global();
#pragma unroll 1
            for (int s = 0; s < 28; s++) {
                if (s >= 1 && s < 6) mbar_wait(BAR(B_FULL + s - 1), 0);
                const int ps = s < 14 ? 0 : s < 21 ? 1 : 2;
                const uint32_t half = ps < 2 ? 8192 : 4096;
                mbar_wait(BAR(B_EMPTY + sl), (s >= 7 && s < 14) || s >= 21);
                expect_e(BAR(B_FULL + sl), half);
                tma3_e(sb + slot_off(sl) + sec * half, &p.ga + 2 * ps + sec, 0, ps ? 64 * sl : 32 * s, ps == 0 ? fa >> 6 : ps == 1 ? fb >> 6 : fc >> 5, BAR(B_FULL + sl));
                sl = sl == 6 ? 0 : sl + 1;
            }
            if (!sec) PROFH(3);
#pragma unroll 1
            for (int e = 0; e < 4; e++) {
                const uint32_t dst = sb + slot_off(e) + sec * 8192, bar = BAR(B_FULL + e);
                const int f = (e < 2 ? fa + 64 * e : e == 2 ? fb : fc) + 32 * sec;
                mbar_wait(BAR(B_EMPTY + e), 0);
                expect_e(bar, e == 3 && sec ? 0 : 7168);
                if (!(e == 3 && sec)) { LOADW }
            }
            sl = 4;
            int e = 4;
#pragma unroll 1
            for (int grp = 0; grp < 9; grp++) {
                const int ps = grp >= 6 ? 2 : grp >= 3 ? 1 : 0;
                int sidx = grp - 3 * ps;
                if (sec && sidx == 0) { mbar_wait(BAR(B_HRDY + ps), 0); fence_async_global(); }
                sidx += sidx >= nq;
                int f = pass_f(4 * kh + sidx, ps);
#pragma unroll 1
                for (int k = 4 >> ps; k > 0; k--, e++, f += 32) {
                    const uint32_t dst = sb + slot_off(sl), bar = BAR(B_FULL + sl);
                    mbar_wait(BAR(B_EMPTY + sl), e >= 12 && e < 24);
                    if (e < WIN_END && e >= WIN) mbar_wait(BAR(B_FULL + (sl >= WIN ? sl - WIN : sl + 12 - WIN)), e - WIN >= 12);
                    expect_e(bar, sec ? 8192 : 7168);
                    if (!sec) { LOADW }
                    else bulk_e(dst + 8192, g_h2 + (size_t)r * (224 * 512) + f * 64, 8192, bar);
                    sl = sl == 11 ? 0 : sl + 1;
                }
            }
            if (!sec) PROFH(4);
}

__global__ void __cluster_dims__(2, 1, 1) __launch_bounds__(384, 1) fused_block_kernel(const __grid_constant__ Params p) {
    extern __shared__ __align__(1024) unsigned char smem[];
    const uint32_t sb = (uint32_t)__cvta_generic_to_shared(smem);
    const int tid = threadIdx.x, lane = tid & 31, warp = __shfl_sync(~0u, tid >> 5, 0);
    const int m = blockIdx.x >> 1;
    int r, nq;
    {
        int g, i;
        if (m < MAP_S) { g = m < 4 ? 15 : 16; i = m & 3; }
        else if (m < MAP_S + 32) { g = (m - MAP_S) & 7; i = (m - MAP_S) >> 3; }
        else if (m < MAP_S + 60) { i = (m - MAP_S - 32) / 7; g = 8 + (m - MAP_S - 32) - 7 * i; }
        else { g = 16; i = m & 3; }
        r = g; nq = i;
    }
    const int j = opaque(2 * nq + (blockIdx.x & 1)), b = 8 * r + j, fs = 4 * kh + nq;
    const uint32_t sc = r == 16;
    if (lane == 0 && warp < 9 && warp != 6 && warp != 7) {
        const int i0 = warp == 8 ? 0 : 8 + 8 * warp, cnt = warp == 0 || warp == 8 ? 1 : warp < 3 ? 2 : 8;
#pragma unroll
        for (int k = 0; k < 8; k++) if (i0 + k != B_WMFULL) mbar_init(BAR(i0 + k), cnt);
        asm volatile("fence.mbarrier_init.release.cluster;" ::: "memory");
        fence_async_smem();
    }

    if (warp < 8) {
        const int w = warp >> 2, wi = warp & 3;
#define COORDS const int t = fresh_tid() & 127, lane = t & 31, q = lane & 3, lr = lane >> 2, ra = 64 * w + 16 * wi + lr; \
        const uint32_t lx = (lane >> 4) ^ (lane & 7), mrow = (64 * w + 16 * wi + ((lane >> 3) & 1) * 8 + (lane & 7)) * 128; \
        (void)q; (void)lr; (void)ra; (void)lx; (void)mrow;
        const int sid = 2 * (j & 3) + w;
#define RUN(k) (!sc || sid == (k))
#define WAIT(i, par) mbar_wait_c(BAR(i), (par) | sc)
        constexpr uint64_t DB128 = dconst(4096, 1024, 1);
        bar_arrive(9, 384);
        bar_sync(0, 384);
        asm volatile("barrier.cluster.arrive.relaxed.aligned;" ::: "memory");
        asm volatile("setmaxnreg.inc.sync.aligned.u32 224;");
        PROFC(0);
        uint32_t xr[16];
        {
            COORDS
            uint32_t h[112];
            if (RUN(0)) {
                float ds[4] = {}, da[2][4] = {}, db[2][4] = {};
                const uint32_t ONE2 = 0x3F803F80u;
                if (kh == 0) { WAIT(B_WMFULL, 0); gemv_part(sb + OFF_Y + HALF, 1, warp, lane); warp_arrive(BAR(B_GEMV)); }
#pragma unroll
                for (int kb = 0; kb < 7; kb++) {
                    WAIT(B_XFULL + kb, 0);
#pragma unroll
                    for (int k4 = 0; k4 < 4; k4++) ldsm4(sb + OFF_X + mrow + kb * 16384 + (((2 * k4) ^ lx) << 4), h + 16 * kb + 4 * k4);
#pragma unroll
                    for (int k4 = 0; k4 < 4; k4++) {
                        const uint32_t* f = h + 16 * kb + 4 * k4;
                        mma16816(ds, f[0], f[1], f[2], f[3], ONE2, ONE2);
                        mma1688(da[0], f[0], f[1], f[0]); mma1688(db[0], f[0], f[1], f[1]);
                        mma1688(da[1], f[2], f[3], f[2]); mma1688(db[1], f[2], f[3], f[3]);
                    }
                }
#pragma unroll
                for (int i = 0; i < 4; i++) {
                    const int ch = 7 * j + 2 * i + (lane >> 4);
                    ldsm4(sb + OFF_X + mrow + (ch >> 3) * 16384 + (((ch ^ lane) & 7) << 4), xr + 4 * i);
                }
                warp_arrive(BAR(B_XFREE));
                float qa = (lr & 1) ? da[0][1] + da[1][1] : da[0][0] + da[1][0];
                float qb = (lr & 1) ? db[0][3] + db[1][3] : db[0][2] + db[1][2];
                const int src = (lane & ~3) | (lr >> 1);
                qa = __shfl_sync(~0u, qa, src);
                qb = __shfl_sync(~0u, qb, src);
                uint32_t ra2, na2, rb2, nb2;
                ln_coeffs(ds[0] * (1.f / DM), qa * (1.f / DM), ra2, na2);
                ln_coeffs(ds[2] * (1.f / DM), qb * (1.f / DM), rb2, nb2);
#pragma unroll
                for (int i = 0; i < 112; i += 2) { h[i] = hfma2(h[i], ra2, na2); h[i + 1] = hfma2(h[i + 1], rb2, nb2); }
                if (kh == 1) { WAIT(B_WMFULL, 0); gemv_part(sb + OFF_Y + HALF, 2, warp, lane); warp_arrive(BAR(B_GEMV)); }
            } else { reg_def<112>(h); reg_def<16>(xr); }
            PROFC(1);
            if (RUN(1)) {
                float ak[28], av[28], aq[28];
                uint32_t kp[14], vp[14];
                const uint32_t bk0 = mkdesc(sb + OFF_Y, DB128) + kh, bv0 = mkdesc(sb + OFF_Y + HALF, DB128) + kh, bq0 = mkdesc(sb + OFF_X, DB128) + kh;
                uint32_t* kvg = g_kv + (size_t)(b * 2) * 3584 + (8 * w + 2 * wi) * 224 + lane;
                WAIT(B_FULLK, 0);
                WAIT(B_MOD1, 0);
                PROFC(2);
                reg_def<28>(ak);
#pragma unroll
                for (int g4 = 0; g4 < 4; g4++) {
#pragma unroll
                    for (int ks = 7 * g4; ks < 7 * g4 + 7; ks++) {
                        const uint4 st = *(const uint4*)(smem + M_ST + ks * 64 + q * 16);
                        h[4 * ks] = hfma2(h[4 * ks], st.x, st.y); h[4 * ks + 1] = hfma2(h[4 * ks + 1], st.x, st.y);
                        h[4 * ks + 2] = hfma2(h[4 * ks + 2], st.z, st.w); h[4 * ks + 3] = hfma2(h[4 * ks + 3], st.z, st.w);
                    }
                    WG_FENCE();
#pragma unroll
                    for (int ks = 7 * g4; ks < 7 * g4 + 7; ks++) wgmma_rs_56<DB128>(ak, h[4 * ks], h[4 * ks + 1], h[4 * ks + 2], h[4 * ks + 3], bk0 + ks * 128, ks != 0);
                }
                WG_COMMIT();
                PROFC(3);
                WAIT(B_FULLV, 0);
                reg_def<28>(av);
                WG_FENCE();
#pragma unroll
                for (int ks = 0; ks < 8; ks++) wgmma_rs_56<DB128>(av, h[4 * ks], h[4 * ks + 1], h[4 * ks + 2], h[4 * ks + 3], bv0 + ks * 128, ks != 0);
                WG_COMMIT();
                WG_WAIT(1);
                reg_fence<28>(ak);
#pragma unroll
                for (int g = 0; g < 7; g++) {
                    kp[2 * g] = pack2(ak[4 * g], ak[4 * g + 1]); kp[2 * g + 1] = pack2(ak[4 * g + 2], ak[4 * g + 3]);
                    kvg[g * 32] = kp[2 * g]; kvg[224 + g * 32] = kp[2 * g + 1];
                }
                warp_arrive(BAR(B_PUB));
                PROFC(4);
                WG_FENCE();
#pragma unroll
                for (int ks = 8; ks < 28; ks++) wgmma_rs_56<DB128>(av, h[4 * ks], h[4 * ks + 1], h[4 * ks + 2], h[4 * ks + 3], bv0 + ks * 128, 1);
                WG_COMMIT();
                WAIT(B_FULLQ, 0);
                reg_def<28>(aq);
                WG_FENCE();
#pragma unroll
                for (int ks = 0; ks < 8; ks++) wgmma_rs_56<DB128>(aq, h[4 * ks], h[4 * ks + 1], h[4 * ks + 2], h[4 * ks + 3], bq0 + ks * 128, ks != 0);
                WG_COMMIT();
                WG_WAIT(1);
                reg_fence<28>(av);
#pragma unroll
                for (int g = 0; g < 7; g++) {
                    vp[2 * g] = pack2(av[4 * g], av[4 * g + 1]); vp[2 * g + 1] = pack2(av[4 * g + 2], av[4 * g + 3]);
                    kvg[3584 + g * 32] = vp[2 * g]; kvg[3584 + 224 + g * 32] = vp[2 * g + 1];
                }
                warp_arrive(BAR(B_PUB + 1));
                PROFC(5);
                WG_FENCE();
#pragma unroll
                for (int ks = 8; ks < 28; ks++) wgmma_rs_56<DB128>(aq, h[4 * ks], h[4 * ks + 1], h[4 * ks + 2], h[4 * ks + 3], bq0 + ks * 128, 1);
                WG_COMMIT();
                WAIT(B_PUB + 1, 0);
                const uint32_t ko = sb + OFF_Y + Y_KOWN + (8 * w + 2 * wi) * 896 + lane * 4;
                const uint32_t qo = sb + OFF_Y + Y_Q + (8 * w + 2 * wi) * 1024 + lane * 4;
#pragma unroll
                for (int g = 0; g < 7; g++) {
                    sts1(ko + g * 128, kp[2 * g]); sts1(ko + 896 + g * 128, kp[2 * g + 1]);
                    sts1(ko + (Y_VOWN - Y_KOWN) + g * 128, vp[2 * g]); sts1(ko + (Y_VOWN - Y_KOWN) + 896 + g * 128, vp[2 * g + 1]);
                }
                WG_WAIT(0);
                reg_fence<28>(aq);
                __syncwarp();
                if (lane < 3 && w == 1) mbar_arrive(BAR(B_EMPTY + lane));
#pragma unroll
                for (int g = 0; g < 7; g++) {
                    const uint32_t q0 = pack2(aq[4 * g], aq[4 * g + 1]), q1 = pack2(aq[4 * g + 2], aq[4 * g + 3]);
                    if (g == 3) {
                        sts1(qo + 3 * 128, q < 2 ? q0 : 0u); sts1(qo + 1024 + 3 * 128, q < 2 ? q1 : 0u);
                        sts1(qo + 4 * 128, q < 2 ? 0u : q0); sts1(qo + 1024 + 4 * 128, q < 2 ? 0u : q1);
                    } else {
                        const int ch = g < 3 ? g : g + 1;
                        sts1(qo + ch * 128, q0); sts1(qo + 1024 + ch * 128, q1);
                    }
                }
                if (!sc) bar_sync(3, 256);
            }
        }
        PROFC(6);
        WAIT(B_KRFULL, 0);
        PROFC(7);
        if (RUN(2)) {
#pragma unroll 1
            for (int hf = sc; hf < 2; hf++) {
                COORDS
                float s[136];
                float na = 0.f, nb = 0.f;
                const float CS = 0.18898223650461361f * 1.4426950408889634f;
                const int kg0 = 8 * hf + 2 * wi;
                const int pmin = 16 - 8 * r - 4 * hf - wi;
                const float NEG = __int_as_float(0xFF800000);
                {
                    uint32_t F[8];
                    const uint32_t qa = sb + OFF_Y + Y_Q + (kg0 + ((lane >> 3) & 1)) * 1024 + (4 * w + (lane >> 4)) * 128 + (lane & 7) * 16;
                    ldsm4(qa, F); ldsm4(qa + 256, F + 4);
                    uint32_t ka = sb + OFF_Y + Y_K + kg0 * 896 + (3 * w + (lane >> 3)) * 128 + (lane & 7) * 16;
#pragma unroll
                    for (int g = 0; g < 34; g++) {
                        uint32_t B[4];
                        if (g >= 12 && g % 4 == 0) ka += __float_as_uint(s[4 * (g - 12)]) & p.zero;
                        ldsm4(ka + g * 896, B);
                        mma16816_first(s + 4 * g, F[0], F[1], F[2], F[3], B[0], B[1]);
                        mma16816_v(s + 4 * g, F[4], F[5], F[6], F[7], B[2], B[3]);
                    }
                    const bool c0 = 2 * q > lr, c1 = 2 * q + 1 > lr;
                    if (!c0) { s[0] = NEG; s[6] = NEG; }
                    if (!c1) { s[1] = NEG; s[7] = NEG; }
                    s[2] = NEG; s[3] = NEG;
                    if (c0) { s[128] = NEG; s[134] = NEG; }
                    if (c1) { s[129] = NEG; s[135] = NEG; }
                    s[132] = NEG; s[133] = NEG;
                    float ma = NEG, mb = NEG;
#pragma unroll
                    for (int pp = 0; pp < 17; pp++) {
                        const float* e = s + 8 * pp;
                        const float bias = pp < pmin ? NEG : 0.f;
                        ma = fmaxf(ma, fmaxf(fmaxf(e[0], e[1]), fmaxf(e[4], e[5])) + bias);
                        mb = fmaxf(mb, fmaxf(fmaxf(e[2], e[3]), fmaxf(e[6], e[7])) + bias);
                    }
                    ma = fmaxf(ma, __shfl_xor_sync(~0u, ma, 1)); mb = fmaxf(mb, __shfl_xor_sync(~0u, mb, 1));
                    ma = fmaxf(ma, __shfl_xor_sync(~0u, ma, 2)); mb = fmaxf(mb, __shfl_xor_sync(~0u, mb, 2));
                    na = -ma * CS; nb = -mb * CS;
                }
                PROFC(8 + 3 * hf);
                {
                    WAIT(B_VRFULL, 0);
                    float o[16] = {}, rs[4] = {};
                    uint32_t pk[2];
                    const uint32_t va = sb + OFF_Y + Y_VR + (kg0 + ((lane >> 3) & 1)) * 896 + (3 * w + (lane >> 4)) * 128 + (lane & 7) * 16;
#pragma unroll
                    for (int pp = 0; pp < 17; pp++) {
                        uint32_t B[8];
                        const uint32_t v = va + pp * 1792 + (pp == 16 || (pp >= 9 && kg0 + 2 * pp >= 32) ? Y_VOWN - 32 * 896 : 0);
                        ldsm4t(v, B); ldsm4t(v + 256, B + 4);
                        float e[8];
                        const float bias = __uint_as_float((pp < pmin ? 0xFF800000u : 0u) | ((pp < 2 ? B[0] : pk[pp & 1]) & p.zero));
#pragma unroll
                        for (int i = 0; i < 8; i++) e[i] = ex2(fmaf(s[8 * pp + i], CS, ((i & 2) ? nb : na) + bias));
                        const uint32_t p0 = pack2(e[0], e[1]), p1 = pack2(e[2], e[3]), p2 = pack2(e[4], e[5]), p3 = pack2(e[6], e[7]);
                        pk[pp & 1] = p3;
                        mma16816(rs, p0, p1, p2, p3, 0x3F803F80u, 0x3F803F80u);
#pragma unroll
                        for (int g = 0; g < 4; g++) mma16816(o + 4 * g, p0, p1, p2, p3, B[2 * g], B[2 * g + 1]);
                    }
                    PROFC(9 + 3 * hf);
                    const float ia = rcp(rs[0]), ib = rcp(rs[2]);
                    uint32_t* og = g_o + (size_t)(2 * r + hf) * 14336 + (7 * j + 3 * w) * 256 + wi * 64 + lane;
#pragma unroll
                    for (int g = 0; g < 4; g++) {
                        if ((g == 3 - 3 * w) ? ((q >> 1) == w) : true) {
                            og[g * 256] = pack2(o[4 * g] * ia, o[4 * g + 1] * ia);
                            og[g * 256 + 32] = pack2(o[4 * g + 2] * ib, o[4 * g + 3] * ib);
                        }
                    }
                    warp_arrive(BAR(B_PUB + 2 + hf));
                    PROFC(10 + 3 * hf);
                }
            }
        }
        uint32_t x1p[14];
        COORDS
        constexpr uint64_t DT = dconst(1024, 128, 0);
        const int tile = opaque((lds1(sb + M_EPOCH) & 1) * 34 + 2 * r + w);
        if (RUN(4)) {
            float ac[28];
            const uint32_t ad = mkdesc(sb + (w ? OFF_Y + HALF : OFF_X), DT), bd = mkdesc(sb + OFF_X + HALF, DB128) + kh;
            WAIT(B_WOFULL, 0);
            WAIT(B_MOD2, 0);
            WAIT(B_GFULL + w, 0);
            PROFC(28);
            reg_def<28>(ac);
#pragma unroll 1
            for (int u = 0; u < 4; u++) {
                if (u == 2) WAIT(B_XFULL + 2 + w, 1);
                WG_FENCE();
#pragma unroll
                for (int i = 0; i < 7; i++) wgmma_ss_56<DT, DB128>(ac, ad + (7 * u + i) * 128, bd + (7 * u + i) * 128, (u | i) != 0);
            }
            WG_COMMIT();
            WG_WAIT(0);
            reg_fence<28>(ac);
            PROFC(14);
            __syncwarp();
            if (lane < 3) mbar_arrive(BAR(B_EMPTY + 3 + lane));
            if (lane < 3 && w == 0) mbar_arrive(BAR(B_EMPTY + lane));
            float s1a = 0.f, s2a = 0.f, s1b = 0.f, s2b = 0.f;
            uint32_t* xo = g_x1 + (size_t)tile * 14336 + 7 * j * 256 + wi * 64 + lane;
#pragma unroll
            for (int g = 0; g < 7; g++) {
                const float2 ga = *(const float2*)(smem + M_G + (8 * g + 2 * q) * 4);
                x1p[2 * g] = pack2(fmaf(ga.x, ac[4 * g], bf_lo(xr[2 * g])), fmaf(ga.y, ac[4 * g + 1], bf_hi(xr[2 * g])));
                x1p[2 * g + 1] = pack2(fmaf(ga.x, ac[4 * g + 2], bf_lo(xr[2 * g + 1])), fmaf(ga.y, ac[4 * g + 3], bf_hi(xr[2 * g + 1])));
                st_relaxed(xo + g * 256, max(x1p[2 * g], 1u)); st_relaxed(xo + g * 256 + 32, max(x1p[2 * g + 1], 1u));
                const float u0 = bf_lo(x1p[2 * g]), u1 = bf_hi(x1p[2 * g]), u2 = bf_lo(x1p[2 * g + 1]), u3 = bf_hi(x1p[2 * g + 1]);
                s1a += u0 + u1; s2a += u0 * u0 + u1 * u1; s1b += u2 + u3; s2b += u2 * u2 + u3 * u3;
            }
            float ka = (q & 1) ? s2a : s1a, kb2 = (q & 1) ? s2b : s1b;
            ka += __shfl_xor_sync(~0u, (q & 1) ? s1a : s2a, 1); kb2 += __shfl_xor_sync(~0u, (q & 1) ? s1b : s2b, 1);
            const float kk = ((q & 2) ? kb2 : ka) + __shfl_xor_sync(~0u, (q & 2) ? ka : kb2, 2);
            st_relaxed((uint32_t*)g_st + ((tile * 8 + j) * 64 + 16 * wi + lr + 4 * (q & 2)) * 2 + (q & 1), max(__float_as_uint(kk), 1u));
            __syncwarp();
            if (lane < 2) mbar_arrive(BAR(B_PUB + 4 + w));
        } else reg_def<14>(x1p);
        PROFC(15);
        uint32_t h2a[32], h2b[24];
        if (RUN(6)) {
            const int fa = pass_f(fs, 0), fb = pass_f(fs, 1), fc = pass_f(fs, 2);
            uint32_t* h2g = g_h2 + (size_t)r * (224 * 512) + (8 * w + 2 * wi) * 32 + lane;
            const uint32_t a0 = mkdesc(sb + OFF_Y + w * HALF, DT);
            {
                WAIT(B_GFULL + 2 + w, 0);
                PROFC(16);
                float2 sa, sbb;
                {
                    uint2 u[16];
#pragma unroll
                    for (int i = 0; i < 16; i++) { const float2 v = lds2f(sb + OFF_X + X_STAT + w * 4096 + ((i >> 1) * 64 + 16 * wi + lr + 8 * (i & 1)) * 8); u[i] = make_uint2(__float_as_uint(v.x), __float_as_uint(v.y)); }
#pragma unroll 1
                    for (;;) {
                        uint32_t mn = ~0u;
#pragma unroll
                        for (int i = 0; i < 16; i++) mn = min(mn, min(u[i].x, u[i].y));
                        if (!__any_sync(~0u, mn == 0u) || sc) break;
#pragma unroll
                        for (int i = 0; i < 16; i++) u[i] = ld_relaxed2(g_st + (tile * 8 + (i >> 1)) * 64 + 16 * wi + lr + 8 * (i & 1));
                    }
                    sa = make_float2(0.f, 0.f); sbb = sa;
#pragma unroll
                    for (int i = 0; i < 16; i += 2) {
                        sa.x += __uint_as_float(u[i].x); sa.y += __uint_as_float(u[i].y);
                        sbb.x += __uint_as_float(u[i + 1].x); sbb.y += __uint_as_float(u[i + 1].y);
                    }
                }
                warp_arrive(BAR(B_EMPTY + 6));
                uint32_t ra2, na2, rb2, nb2;
                ln_coeffs(sa.x * (1.f / DM), sa.y * (1.f / DM), ra2, na2);
                ln_coeffs(sbb.x * (1.f / DM), sbb.y * (1.f / DM), rb2, nb2);
                const uint32_t ha = sb + OFF_Y + w * HALF + (lane >> 4) * 1024 + (2 * wi + ((lane >> 3) & 1)) * 128 + (lane & 7) * 16;
                const uint32_t sta = sb + M_ST + q * 16;
                const uint32_t* xg = g_x1 + (size_t)tile * 14336 + wi * 64 + lane;
                auto prep = [&](int s, uint32_t* f) {
                    uint32_t x[8];
                    if (s == 4) WAIT(B_XFULL + 4 + w, 1);
                    ldsm4(ha + s * 4096, x); ldsm4(ha + s * 4096 + 2048, x + 4);
                    while (__any_sync(~0u, min(min(min(x[0], x[1]), min(x[2], x[3])), min(min(x[4], x[5]), min(x[6], x[7]))) == 0u) && !sc) {
#pragma unroll
                        for (int i = 0; i < 8; i++) x[i] = ld_relaxed(xg + (4 * s + (i >> 1)) * 256 + (i & 1) * 32);
                    }
                    const uint4 st[2] = {lds4(sta + s * 128), lds4(sta + s * 128 + 64)};
#pragma unroll
                    for (int i = 0; i < 2; i++) {
                        f[4 * i] = hfma2(hfma2(x[4 * i], ra2, na2), st[i].x, st[i].y); f[4 * i + 1] = hfma2(hfma2(x[4 * i + 1], rb2, nb2), st[i].x, st[i].y);
                        f[4 * i + 2] = hfma2(hfma2(x[4 * i + 2], ra2, na2), st[i].z, st[i].w); f[4 * i + 3] = hfma2(hfma2(x[4 * i + 3], rb2, nb2), st[i].z, st[i].w);
                    }
                    stsm4(ha + s * 4096, f[0], f[1], f[2], f[3]); stsm4(ha + s * 4096 + 2048, f[4], f[5], f[6], f[7]);
                };
                float ac[128];
                uint32_t fr[3][8];
                const uint32_t bx = mkdesc(sb, DB128);
                reg_def<128>(ac);
                prep(0, fr[0]);
                PROFC(17);
#pragma unroll
                for (int s = 0; s < 14; s++) {
                    const uint32_t* f = fr[s % 3];
                    const uint32_t bd = bx + (slot_off(s % 7) >> 4);
                    WAIT(B_FULL + s % 7, s >= 7);
                    WG_FENCE();
                    wgmma_rs_256<DB128>(ac, f[0], f[1], f[2], f[3], bd, s != 0);
                    wgmma_rs_256<DB128>(ac, f[4], f[5], f[6], f[7], bd + 128, 1);
                    WG_COMMIT();
                    if (s < 13) prep(s + 1, fr[(s + 1) % 3]);
                    if (s > 0) { WG_WAIT(1); warp_arrive(BAR(B_EMPTY + (s - 1) % 7)); }
                }
                PROFC(18);
                fence_async_smem();
                WG_WAIT(0);
                reg_fence<128>(ac);
                warp_arrive(BAR(B_EMPTY + 6));
#pragma unroll
                for (int g = 0; g < 16; g++) {
                    h2a[2 * g] = hmul2(pack2_relu(ac[4 * g], ac[4 * g + 1]), pack2(ac[64 + 4 * g], ac[64 + 4 * g + 1]));
                    h2a[2 * g + 1] = hmul2(pack2_relu(ac[4 * g + 2], ac[4 * g + 3]), pack2(ac[64 + 4 * g + 2], ac[64 + 4 * g + 3]));
                    h2g[(fa / 8 + g) * 512] = h2a[2 * g]; h2g[(fa / 8 + g) * 512 + 32] = h2a[2 * g + 1];
                }
                warp_arrive(BAR(B_PUB + 6));
                bar_sync(1 + w, 128);
            }
            PROFC(19);
            {
                float ac[64];
                reg_def<64>(ac);
                const uint32_t bx = mkdesc(sb, dconst(8192, 1024, 1));
#pragma unroll kB
                for (int s = 0; s < 7; s++) {
                    WAIT(B_FULL + s, 0);
                    const uint32_t ad = a0 + s * 512, bd = bx + (slot_off(s) >> 4);
                    WG_FENCE();
#pragma unroll
                    for (int k = 0; k < 4; k++) wgmma_ss_128<DT, DB128>(ac, ad + k * 128, bd + k * 128, (s | k) != 0);
                    WG_COMMIT();
                    if (s > 0) { WG_WAIT(1); warp_arrive(BAR(B_EMPTY + s - 1)); }
                }
                WG_WAIT(0);
                reg_fence<64>(ac);
                warp_arrive(BAR(B_EMPTY + 6));
#pragma unroll
                for (int g = 0; g < 8; g++) {
                    h2b[2 * g] = hmul2(pack2_relu(ac[4 * g], ac[4 * g + 1]), pack2(ac[32 + 4 * g], ac[32 + 4 * g + 1]));
                    h2b[2 * g + 1] = hmul2(pack2_relu(ac[4 * g + 2], ac[4 * g + 3]), pack2(ac[32 + 4 * g + 2], ac[32 + 4 * g + 3]));
                    h2g[(fb / 8 + g) * 512] = h2b[2 * g]; h2g[(fb / 8 + g) * 512 + 32] = h2b[2 * g + 1];
                }
                warp_arrive(BAR(B_PUB + 7));
            }
            PROFC(27);
            {
                float ac[32];
                reg_def<32>(ac);
                const uint32_t bx = mkdesc(sb, dconst(4096, 512, 2));
#pragma unroll kC
                for (int s = 0; s < 7; s++) {
                    WAIT(B_FULL + s, 1);
                    const uint32_t ad = a0 + p.zero + s * 512, bd = bx + (slot_off(s) >> 4);
                    WG_FENCE();
#pragma unroll
                    for (int k = 0; k < 4; k++) wgmma_ss_64<DT, dconst(4096, 512, 2)>(ac, ad + k * 128, bd + k * 64, (s | k) != 0);
                    WG_COMMIT();
                    if (s > 0) { WG_WAIT(1); warp_arrive(BAR(B_EMPTY + s - 1)); }
                }
                WG_WAIT(0);
                reg_fence<32>(ac);
                __syncwarp();
                if (lane < 6) mbar_arrive(BAR(B_EMPTY + 6 + lane));
                PROFC(20);
#pragma unroll
                for (int g = 0; g < 4; g++) {
                    h2b[16 + 2 * g] = hmul2(pack2_relu(ac[4 * g], ac[4 * g + 1]), pack2(ac[16 + 4 * g], ac[16 + 4 * g + 1]));
                    h2b[16 + 2 * g + 1] = hmul2(pack2_relu(ac[4 * g + 2], ac[4 * g + 3]), pack2(ac[16 + 4 * g + 2], ac[16 + 4 * g + 3]));
                    h2g[(fc / 8 + g) * 512] = h2b[16 + 2 * g]; h2g[(fc / 8 + g) * 512 + 32] = h2b[16 + 2 * g + 1];
                }
                warp_arrive(BAR(B_PUB + 8));
                asm volatile("barrier.cluster.wait.aligned;" ::: "memory");
                if (lane == 0 && !sc) {
                    uint32_t rb;
                    asm volatile("mapa.shared::cluster.u32 %0, %1, %2;" : "=r"(rb) : "r"(BAR(B_PEER)), "r"(kh ^ 1));
                    asm volatile("mbarrier.arrive.relaxed.cluster.shared::cluster.b64 _, [%0];" ::"r"(rb) : "memory");
                }
            }
        } else { reg_def<32>(h2a); reg_def<24>(h2b); }
        PROFC(21);
        if (RUN(7)) {
            float ac[56];
            reg_def<56>(ac);
            constexpr uint64_t DAN = dconst(2048, 128, 0);
            constexpr uint64_t DW = dconst(128, 512, 0);
            const uint32_t bx = mkdesc(sb, DW);
#pragma unroll
            for (int e = 0; e < 4; e++) {
                WAIT(B_FULL + e, 0);
                const uint32_t bd = bx + (slot_off(e) >> 4);
                const uint32_t* hh = e < 2 ? h2a + 16 * e : h2b + 16 * (e - 2);
                WG_FENCE();
#pragma unroll
                for (int k = 0; k < (e < 3 ? 4 : 2); k++) wgmma_rs_112<DW>(ac, hh[4 * k], hh[4 * k + 1], hh[4 * k + 2], hh[4 * k + 3], bd + (k >> 1) * 512 + (k & 1) * 16, (e | k) != 0);
                WG_COMMIT();
                if (e > 0) { WG_WAIT(1); warp_arrive(BAR(B_EMPTY + e - 1)); }
            }
            PROFC(22);
            const uint32_t ax = mkdesc(sb + 8192 + w * 1024, DAN);
#pragma unroll kG2
            for (int e = 4; e < 25; e++) {
                WAIT(B_FULL + e % 12, e >= 12 && e < 24);
                if (e == 16) PROFC(23);
                const uint32_t z = (e / 12) * p.zero;
                const uint32_t ad = ax + z + (slot_off(e % 12) >> 4), bd = bx + z + (slot_off(e % 12) >> 4);
                WG_FENCE();
                wgmma_ss_112<DAN, DW>(ac, ad, bd, 1);
                wgmma_ss_112<DAN, DW>(ac, ad + 256, bd + 16, 1);
                WG_COMMIT();
                if (e < 14) { WG_WAIT(1); warp_arrive(BAR(B_EMPTY + (e - 1) % 12)); }
            }
            mbar_wait_cluster(BAR(B_PEER), sc);
            WG_WAIT(0);
            reg_fence<56>(ac);
            PROFC(24);
            uint32_t rdst, rbar;
            asm volatile("mapa.shared::cluster.u32 %0, %1, %2;" : "=r"(rdst) : "r"(sb + OFF_Y + (5 + w) * 16384 + t * 16), "r"(kh ^ 1 ^ sc));
            asm volatile("mapa.shared::cluster.u32 %0, %1, %2;" : "=r"(rbar) : "r"(BAR(B_XCH + w)), "r"(kh ^ 1 ^ sc));
#define ACG(g, i) ac[4 * (g) + (i)]
#pragma unroll
            for (int g = 0; g < 7; g++) {
                const float v0 = kh ? ACG(g, 0) : ACG(g + 7, 0), v1 = kh ? ACG(g, 1) : ACG(g + 7, 1);
                const float v2 = kh ? ACG(g, 2) : ACG(g + 7, 2), v3 = kh ? ACG(g, 3) : ACG(g + 7, 3);
                if (!sc) asm volatile("st.async.shared::cluster.mbarrier::complete_tx::bytes.v4.f32 [%0], {%1,%2,%3,%4}, [%5];"
                             ::"r"(rdst + g * 2048), "f"(v0), "f"(v1), "f"(v2), "f"(v3), "r"(rbar) : "memory");
            }
            mbar_wait_cluster(BAR(B_XCH + w), sc);
            PROFC(25);
            bf16* og = (sc ? (bf16*)(g_h2 + 16 * 224 * 512) : p.out + (size_t)128 * r * DM) + (size_t)ra * DM + 56 * j + 2 * q;
#pragma unroll
            for (int g = 0; g < 7; g++) {
                const uint4 rv = *(const uint4*)(smem + OFF_Y + (5 + w) * 16384 + t * 16 + g * 2048);
                const float2 gb = *(const float2*)(smem + M_G + 224 + (8 * g + 2 * q) * 4);
                const float v0 = (kh ? ACG(g + 7, 0) : ACG(g, 0)) + __uint_as_float(rv.x), v1 = (kh ? ACG(g + 7, 1) : ACG(g, 1)) + __uint_as_float(rv.y);
                const float v2 = (kh ? ACG(g + 7, 2) : ACG(g, 2)) + __uint_as_float(rv.z), v3 = (kh ? ACG(g + 7, 3) : ACG(g, 3)) + __uint_as_float(rv.w);
                *(uint32_t*)(og + 8 * g) = pack2(fmaf(gb.x, v0, bf_lo(x1p[2 * g])), fmaf(gb.y, v1, bf_hi(x1p[2 * g])));
                *(uint32_t*)(og + 8 * DM + 8 * g) = pack2(fmaf(gb.x, v2, bf_lo(x1p[2 * g + 1])), fmaf(gb.y, v3, bf_hi(x1p[2 * g + 1])));
            }
        }
        PROFC(26);
        bar_sync(1 + w, 128);
        if (wi == 0) warp_arrive(BAR(B_DONE));
    } else {
        const int lane = fresh_tid() & 31;
        const bool early = kh == 0, gemv = r < 14;
        const int mcol = early ? 16 * (4 * r + nq) : 2 * DM + 32 * (4 * r + nq);
        const uint32_t wmbuf = sb + OFF_Y + HALF;
        asm volatile("setmaxnreg.dec.sync.aligned.u32 56;");
        if (warp == 9) {
#pragma unroll
            for (int i = 56; i < 64; i++) init_e(BAR(i), 1);
            fence_async_smem();
        }
        if (warp == 8) { init_e(BAR(B_WMFULL), 2); fence_async_smem(); }
        bar_arrive(0, 384);
        asm volatile("barrier.cluster.arrive.relaxed.aligned;" ::: "memory");
        uint32_t target = 0;
        if (warp == 8) {
            if (!sc) {
                expect_e(BAR(B_WMFULL), gemv ? 28672 >> early : 0);
                if (early && gemv) { tma3_e(wmbuf, &p.wm, mcol, 0, 0, BAR(B_WMFULL)); tma3_e(wmbuf + 7168, &p.wm, mcol, 224, 0, BAR(B_WMFULL)); }
#pragma unroll 1
                for (int kb = 0; kb < 7; kb++) {
                    expect_e(BAR(B_XFULL + kb), 16384);
                    tma3_e(sb + OFF_X + kb * 16384, &p.xm, 64 * kb, 128 * r, 0, BAR(B_XFULL + kb));
                }
            }
#pragma unroll 1
            for (int mt = 0; mt < 4; mt++) {
                if (mt == 1) {
                    if (!early && gemv) {
#pragma unroll 1
                        for (int k = 0; k < 4; k++) tma3_e(wmbuf + k * 7168, &p.wm, mcol + (k >> 1) * 16, (k & 1) * 224, 0, BAR(B_WMFULL));
                    }
                    bar_sync(9, 384);
                    if (sc) return;
                    mbar_wait(BAR(B_MOD1), 0);
                    mbar_wait(BAR(B_WMFREE), 0);
                }
                if (mt == 2) mbar_wait(BAR(B_XFREE), 0);
                if (mt == 3) mbar_wait(BAR(B_VRFULL), 0);
                const uint32_t bar = BAR(mt == 3 ? B_WOFULL : B_FULLK + mt), dst = sb + (mt < 2 ? OFF_Y : OFF_X) + (mt & 1) * HALF;
                const int c0 = (mt < 2 ? DM + DM * mt : 0) + 56 * j - 8 * kh;
                if (!sc) {
                    expect_e(bar, HALF);
                    tma3_e(dst, mt == 3 ? &p.wo : &p.qkv, c0, 0, 0, bar);
                    tma3_e(dst + HALF / 2, mt == 3 ? &p.wo : &p.qkv, c0, 224, 0, bar);
                }
            }
            expect_e(BAR(B_XCH), 14336);
            expect_e(BAR(B_XCH + 1), 14336);
        } else {
            if (warp == 10 && !sc) {
                l2_prefetch_e((const char*)p.wqkv + (size_t)b * 9408, 9408);
                if (lane == 0) sts1(sb + M_EPOCH, atomicAdd(&g_ticket, 1u) / NCTA);
            }
            if (warp == 11) {
#pragma unroll
                for (int i = 0; i < 8; i++) {
                    const int wd = lane + 32 * i;
                    const uint32_t cb = i < 7 ? __ldg((const uint32_t*)p.c + wd) : 0u;
                    sts1(wmbuf + 28672 + (wd >> 3) * 32 + (wd & 3) * 8 + (wd & 4), pack2(silu_bf(cb & 0xFFFFu), silu_bf(cb >> 16)));
                }
            }
            bar_sync(9, 384);
            if (sc) return;
            target = lds1(sb + M_EPOCH) + 1;
            const uint32_t tag = target & 0xFFFFu;
            if (warp == 11) {
                warp_arrive(BAR(B_WMFULL));
                mbar_wait(BAR(B_GEMV), 0);
                float sum = 0.f;
#pragma unroll
                for (int i = 0; i < 8; i++) sum += *(const float*)(smem + OFF_Y + HALF + 29696 + (i * 32 + (early ? lane & 15 : lane)) * 4);
                const uint32_t word = (pack2(sum, 0.f) << 16) | tag;
                if (gemv) {
                    uint32_t* mg = g_mod + mcol + (early ? (lane & 15) + (lane >> 4) * 4 * 6 * DM : lane);
#pragma unroll
                    for (int i = 0; i < 8; i++) if (i < 4 || !early) st_relaxed(mg + i * 6 * DM, word);
                }
                warp_arrive(BAR(B_WMFREE));
            }
            const uint4* modp = (const uint4*)g_mod + (r & 7) * (6 * DM / 4);
            const bool p2 = warp == 11;
            mbar_wait(BAR(p2 ? B_PUB : B_XFULL + 4), 0);
#pragma unroll 1
            for (int it = p2 ? 0 : warp - 9; it < (p2 ? 2 : warp - 8); it++) {
                const int i0 = lane + 32 * it, imax = p2 ? 251 : 223;
                uint4 v[4];
#pragma unroll 1
                for (int n = 0;; n++) {
                    uint32_t bad = 0;
#pragma unroll
                    for (int k = 0; k < 4; k++) {
                        const int i = min(i0 + 64 * k, imax);
                        v[k] = ld_relaxed4(modp + (i < 224 ? (p2 ? 336 : 0) + i : (i < 238 ? 14 * j + i : 14 * j + i + 322)));
                        bad |= (v[k].x ^ tag) | (v[k].y ^ tag) | (v[k].z ^ tag) | (v[k].w ^ tag);
                    }
                    if (!__any_sync(~0u, bad & 0xFFFFu)) break;
                    if (n > SPIN_LIMIT) __trap();
                }
#pragma unroll
                for (int k = 0; k < 4; k++) {
                    const int i = min(i0 + 64 * k, imax);
                    if (i < 224) {
                        const int isc = i >= 112, c4 = i - 112 * isc;
                        const float one = isc ? 1.f : 0.f;
                        const uint32_t a = sb + M_ST + (c4 >> 2) * 64 + (c4 & 1) * 32 + (c4 & 2) * 4 + (isc ? 0 : 4);
                        sts1(a, pack2(bf_hi(v[k].x) + one, bf_hi(v[k].y) + one));
                        sts1(a + 16, pack2(bf_hi(v[k].z) + one, bf_hi(v[k].w) + one));
                    } else {
                        sts4(sb + M_G + (i - 224) * 16, make_uint4(v[k].x & 0xFFFF0000u, v[k].y & 0xFFFF0000u, v[k].z & 0xFFFF0000u, v[k].w & 0xFFFF0000u));
                    }
                }
                warp_arrive(BAR(p2 ? B_MOD2 : B_MOD1));
            }
            if (warp == 9) {
#pragma unroll 1
                for (int kv = 0; kv < 2; kv++) {
                    mbar_wait(BAR(B_PUB + kv), 0);
                    wait_flags(g_flag + b * 128 + lane, target, (r >= 2 ? 6u : r == 1 ? 2u : 0u) << (8 * kv));
                    fence_async_global();
                    const uint32_t dst = sb + OFF_Y + (kv ? Y_VR : Y_K);
                    expect_e(BAR(B_KRFULL + kv), r >= 2 ? 28672 : r == 1 ? 14336 : 0);
                    if (r >= 2) bulk_e(dst, g_kv + (size_t)((b - 16) * 2 + kv) * 3584, 14336, BAR(B_KRFULL + kv));
                    if (r >= 1) bulk_e(dst + 14336, g_kv + (size_t)((b - 8) * 2 + kv) * 3584, 14336, BAR(B_KRFULL + kv));
                }
            } else if (warp == 11) {
                mbar_wait(BAR(B_VRFULL), 0);
                l2_prefetch_e((const char*)p.wg + (size_t)b * 12544, 12544);
                l2_prefetch_e((const char*)p.wu + (size_t)b * 12544, 12544);
#pragma unroll 1
                for (int k = 0; k < (r < 12 ? 2 : 1); k++) {
                    const int u = 28 * kh + r + 16 * k;
                    expect_e(BAR(B_XFULL + k), 7168);
                    tma3_e(sb + OFF_Y + 102400, &p.dn, 0, 32 * u, 14 * nq, BAR(B_XFULL + k));
                    mbar_wait(BAR(B_XFULL + k), 1);
                    asm volatile("{\n.reg .pred p;\nelect.sync _|p, 0xffffffff;\n@p cp.async.bulk.global.shared::cta.bulk_group [%0], [%1], 7168;\n"
                                 "cp.async.bulk.commit_group;\ncp.async.bulk.wait_group 0;\n}" ::"l"(g_wd + (size_t)(u * 4 + nq) * 1792), "r"(sb + OFF_Y + 102400) : "memory");
                    __syncwarp();
                }
                warp_arrive(BAR(B_WMFREE));
                fence_gpu();
                if (lane < 16) st_relaxed(g_flag + (8 * lane + j) * 128 + 96 + r, target);
            }
        }
        if (warp == 8 || warp == 11) {
            const int sec = warp == 11;
            if (sec) ring_loader<1>(p, sb, r, j, lane); else ring_loader<0>(p, sb, r, j, lane);
            mbar_wait(BAR(B_DONE), 0);
        } else if (warp == 9) {
#pragma unroll
            for (int ev = 0; ev < 4; ev++) { expect_e(BAR(B_GFULL + ev), ev < 2 ? HALF / 2 : 16384 + 4096); expect_e(BAR(B_XFULL + 2 + ev), ev < 2 ? HALF / 2 : HALF - 16384); }
            mbar_wait(BAR(B_PUB + 2), 0);
            const uint32_t* fp = g_flag + b * 128 + 32 + lane;
            const int par = (target - 1) & 1;
#pragma unroll 1
            for (int n = 0, ev = 0; ev < 4; n++) {
                if (ev == 1) { mbar_wait(BAR(B_WMFREE), 1); mbar_wait(BAR(B_PUB + 3), 0); }
                uint32_t ok = __ballot_sync(~0u, (int)(ld_relaxed(fp) - target) >= 0) >> (8 * ev);
                while ((ok & 0xFFu) == 0xFFu) {
                    asm volatile("fence.acquire.gpu;" ::: "memory");
                    fence_async_global();
                    const int tile = 2 * r + (ev & 1) + (ev >> 1) * par * 34;
                    const uint32_t dst = sb + (ev == 0 ? OFF_X : OFF_Y + (ev & 1) * HALF), first = ev < 2 ? HALF / 2 : 16384;
                    const char* src = (const char*)(g_ox + (size_t)((ev >> 1) * 34 + tile) * 14336);
                    if (ev >= 2) bulk_e(sb + OFF_X + X_STAT + (ev & 1) * 4096, g_st + tile * 512, 4096, BAR(B_GFULL + ev));
                    bulk_e(dst, src, first, BAR(B_GFULL + ev));
                    bulk_e(dst + first, src + first, HALF - first, BAR(B_XFULL + 2 + ev));
                    if (ev) PROFH(4 + ev);
                    ev++; ok >>= 8;
                }
                if (n > SPIN_LIMIT) __trap();
            }
            mbar_wait(BAR(B_XFULL + 5), 1);
#pragma unroll 1
            for (int hf = 0; hf < 2; hf++) {
                const int tile = (par ^ 1) * 34 + 2 * r + hf;
                uint4* xz = (uint4*)(g_x1 + (size_t)tile * 14336 + j * 1792) + lane;
#pragma unroll
                for (int i = 0; i < 14; i++) xz[i * 32] = make_uint4(0, 0, 0, 0);
                ((uint4*)(g_st + (tile * 8 + j) * 64))[lane] = make_uint4(0, 0, 0, 0);
            }
#pragma unroll 1
            for (int ps = 0; ps < 3; ps++) {
                mbar_wait(BAR(B_PUB + 6 + ps), 0);
                wait_flags(g_flag + b * 128 + 64 + lane, target, (0x55u << kh) << (8 * ps));
                warp_arrive(BAR(B_HRDY + ps));
                PROFH(9 + ps);
            }
        } else {
#pragma unroll 1
            for (int k = 0; k < 9; k++) {
                uint32_t* fp = k < 2 ? g_flag + (b + 8 * lane) * 128 + k * 8 + lane : g_flag + (8 * r + lane) * 128 + 16 + k * 8 + j;
                mbar_wait(BAR(B_PUB + k), 0);
                if (k != 4 && k != 5) fence_gpu();
                if (k < 2 ? (lane == 1 || lane == 2) : lane < 8) st_relaxed(fp, target);
                if (k >= 3 && k <= 5) PROFH(k - 3);
            }
        }
    }
}

typedef CUresult (*EncodeFn)(CUtensorMap*, CUtensorMapDataType, cuuint32_t, void*, const cuuint64_t*, const cuuint64_t*, const cuuint32_t*,
                             const cuuint32_t*, CUtensorMapInterleave, CUtensorMapSwizzle, CUtensorMapL2promotion, CUtensorMapFloatOOBfill);

static void make_map(EncodeFn fn, CUtensorMap* m, const void* ptr, uint64_t d0, uint64_t d1, uint64_t d2, uint64_t s1, uint64_t s2,
                     uint32_t b0, uint32_t b1, uint32_t b2, CUtensorMapSwizzle sw) {
    cuuint64_t dims[3] = {d0, d1, d2}, strides[2] = {s1, s2};
    cuuint32_t box[3] = {b0, b1, b2}, es[3] = {1, 1, 1};
    CUresult rc = fn(m, CU_TENSOR_MAP_DATA_TYPE_BFLOAT16, 3, (void*)ptr, dims, strides, box, es, CU_TENSOR_MAP_INTERLEAVE_NONE, sw,
                     CU_TENSOR_MAP_L2_PROMOTION_L2_128B, CU_TENSOR_MAP_FLOAT_OOB_FILL_NONE);
    (void)rc;
}

extern "C" void kernel_launch(void* const* d_in, const int* in_sizes, int n_in, void* d_out, int out_size) {
    (void)in_sizes; (void)n_in; (void)out_size;
    static EncodeFn fn = nullptr;
    if (!fn) {
        cudaDriverEntryPointQueryResult st;
        cudaGetDriverEntryPoint("cuTensorMapEncodeTiled", (void**)&fn, cudaEnableDefault, &st);
        cudaFuncSetAttribute(fused_block_kernel, cudaFuncAttributeMaxDynamicSharedMemorySize, SMEM_BYTES);
    }
    Params p;
    p.x = (const bf16*)d_in[0];
    const bf16* wqkv = (const bf16*)d_in[1];
    p.wqkv = wqkv;
    p.wop = (const bf16*)d_in[2];
    p.wg = (const bf16*)d_in[4];
    p.wu = (const bf16*)d_in[5];
    p.wd = (const bf16*)d_in[6];
    p.c = (const bf16*)d_in[7];
    p.wmod = (const bf16*)d_in[8];
    p.out = (bf16*)d_out;
    p.zero = 0;
    make_map(fn, &p.wm, p.wmod, 2688, 448, 1, 5376, 5376 * 448, 16, 224, 1, CU_TENSOR_MAP_SWIZZLE_NONE);
    make_map(fn, &p.xm, p.x, 448, 2048, 1, 896, 896 * 2048, 64, 128, 1, CU_TENSOR_MAP_SWIZZLE_128B);
    make_map(fn, &p.qkv, wqkv, 1344, 448, 1, 2688, 2688 * 448, 64, 224, 1, CU_TENSOR_MAP_SWIZZLE_128B);
    make_map(fn, &p.wo, p.wop, 448, 448, 1, 896, 896 * 448, 64, 224, 1, CU_TENSOR_MAP_SWIZZLE_128B);
    make_map(fn, &p.ga, p.wg, 64, 448, 28, 3584, 128, 64, 32, 2, CU_TENSOR_MAP_SWIZZLE_128B);
    make_map(fn, &p.ua, p.wu, 64, 448, 28, 3584, 128, 64, 32, 2, CU_TENSOR_MAP_SWIZZLE_128B);
    make_map(fn, &p.gb, p.wg, 64, 448, 28, 3584, 128, 64, 64, 1, CU_TENSOR_MAP_SWIZZLE_128B);
    make_map(fn, &p.ub, p.wu, 64, 448, 28, 3584, 128, 64, 64, 1, CU_TENSOR_MAP_SWIZZLE_128B);
    make_map(fn, &p.gc, p.wg, 32, 448, 56, 3584, 64, 32, 64, 1, CU_TENSOR_MAP_SWIZZLE_64B);
    make_map(fn, &p.uc, p.wu, 32, 448, 56, 3584, 64, 32, 64, 1, CU_TENSOR_MAP_SWIZZLE_64B);
    make_map(fn, &p.dn, p.wd, 8, 1792, 56, 896, 16, 8, 32, 14, CU_TENSOR_MAP_SWIZZLE_NONE);
    fused_block_kernel<<<GRID, 384, SMEM_BYTES>>>(p);
}
```

```cpp
#include <cuda_runtime.h>
#include <cuda_bf16.h>
#include <cuda.h>
#include <stdint.h>

typedef __nv_bfloat16 bf16;

template<uint64_t CB> __device__ __forceinline__ void wgmma_rs_56(float* d, uint32_t a0, uint32_t a1, uint32_t a2, uint32_t a3, uint32_t db, int sd) {
  asm volatile("{\n.reg .pred p;\n.reg .b64 b;\nsetp.ne.b32 p, %33, 0;\nmov.b64 b, {%32, %34};\n"
    "wgmma.mma_async.sync.aligned.m64n56k16.f32.bf16.bf16 {%0,%1,%2,%3,%4,%5,%6,%7,%8,%9,%10,%11,%12,%13,%14,%15,%16,%17,%18,%19,%20,%21,%22,%23,%24,%25,%26,%27}, {%28,%29,%30,%31}, b, p, 1, 1, 1;\n}\n"
    : "+f"(d[0]),"+f"(d[1]),"+f"(d[2]),"+f"(d[3]),"+f"(d[4]),"+f"(d[5]),"+f"(d[6]),"+f"(d[7]),"+f"(d[8]),"+f"(d[9]),"+f"(d[10]),"+f"(d[11]),"+f"(d[12]),"+f"(d[13]),"+f"(d[14]),"+f"(d[15]),"+f"(d[16]),"+f"(d[17]),"+f"(d[18]),"+f"(d[19]),"+f"(d[20]),"+f"(d[21]),"+f"(d[22]),"+f"(d[23]),"+f"(d[24]),"+f"(d[25]),"+f"(d[26]),"+f"(d[27])
    : "r"(a0), "r"(a1), "r"(a2), "r"(a3), "r"(db), "r"(sd), "n"((uint32_t)(CB >> 32)));
}
template<uint64_t CA, uint64_t CB> __device__ __forceinline__ void wgmma_ss_56(float* d, uint32_t da, uint32_t db, int sd) {
  asm volatile("{\n.reg .pred p;\n.reg .b64 a, b;\nsetp.ne.b32 p, %30, 0;\nmov.b64 a, {%28, %31};\nmov.b64 b, {%29, %32};\n"
    "wgmma.mma_async.sync.aligned.m64n56k16.f32.bf16.bf16 {%0,%1,%2,%3,%4,%5,%6,%7,%8,%9,%10,%11,%12,%13,%14,%15,%16,%17,%18,%19,%20,%21,%22,%23,%24,%25,%26,%27}, a, b, p, 1, 1, 0, 1;\n}\n"
    : "+f"(d[0]),"+f"(d[1]),"+f"(d[2]),"+f"(d[3]),"+f"(d[4]),"+f"(d[5]),"+f"(d[6]),"+f"(d[7]),"+f"(d[8]),"+f"(d[9]),"+f"(d[10]),"+f"(d[11]),"+f"(d[12]),"+f"(d[13]),"+f"(d[14]),"+f"(d[15]),"+f"(d[16]),"+f"(d[17]),"+f"(d[18]),"+f"(d[19]),"+f"(d[20]),"+f"(d[21]),"+f"(d[22]),"+f"(d[23]),"+f"(d[24]),"+f"(d[25]),"+f"(d[26]),"+f"(d[27])
    : "r"(da), "r"(db), "r"(sd), "n"((uint32_t)(CA >> 32)), "n"((uint32_t)(CB >> 32)));
}
template<uint64_t CB> __device__ __forceinline__ void wgmma_rs_256(float* d, uint32_t a0, uint32_t a1, uint32_t a2, uint32_t a3, uint32_t db, int sd) {
  asm volatile("{\n.reg .pred p;\n.reg .b64 b;\nsetp.ne.b32 p, %133, 0;\nmov.b64 b, {%132, %134};\n"
    "wgmma.mma_async.sync.aligned.m64n256k16.f32.bf16.bf16 {%0,%1,%2,%3,%4,%5,%6,%7,%8,%9,%10,%11,%12,%13,%14,%15,%16,%17,%18,%19,%20,%21,%22,%23,%24,%25,%26,%27,%28,%29,%30,%31,%32,%33,%34,%35,%36,%37,%38,%39,%40,%41,%42,%43,%44,%45,%46,%47,%48,%49,%50,%51,%52,%53,%54,%55,%56,%57,%58,%59,%60,%61,%62,%63,%64,%65,%66,%67,%68,%69,%70,%71,%72,%73,%74,%75,%76,%77,%78,%79,%80,%81,%82,%83,%84,%85,%86,%87,%88,%89,%90,%91,%92,%93,%94,%95,%96,%97,%98,%99,%100,%101,%102,%103,%104,%105,%106,%107,%108,%109,%110,%111,%112,%113,%114,%115,%116,%117,%118,%119,%120,%121,%122,%123,%124,%125,%126,%127}, {%128,%129,%130,%131}, b, p, 1, 1, 1;\n}\n"
    : "+f"(d[0]),"+f"(d[1]),"+f"(d[2]),"+f"(d[3]),"+f"(d[4]),"+f"(d[5]),"+f"(d[6]),"+f"(d[7]),"+f"(d[8]),"+f"(d[9]),"+f"(d[10]),"+f"(d[11]),"+f"(d[12]),"+f"(d[13]),"+f"(d[14]),"+f"(d[15]),"+f"(d[16]),"+f"(d[17]),"+f"(d[18]),"+f"(d[19]),"+f"(d[20]),"+f"(d[21]),"+f"(d[22]),"+f"(d[23]),"+f"(d[24]),"+f"(d[25]),"+f"(d[26]),"+f"(d[27]),"+f"(d[28]),"+f"(d[29]),"+f"(d[30]),"+f"(d[31]),"+f"(d[32]),"+f"(d[33]),"+f"(d[34]),"+f"(d[35]),"+f"(d[36]),"+f"(d[37]),"+f"(d[38]),"+f"(d[39]),"+f"(d[40]),"+f"(d[41]),"+f"(d[42]),"+f"(d[43]),"+f"(d[44]),"+f"(d[45]),"+f"(d[46]),"+f"(d[47]),"+f"(d[48]),"+f"(d[49]),"+f"(d[50]),"+f"(d[51]),"+f"(d[52]),"+f"(d[53]),"+f"(d[54]),"+f"(d[55]),"+f"(d[56]),"+f"(d[57]),"+f"(d[58]),"+f"(d[59]),"+f"(d[60]),"+f"(d[61]),"+f"(d[62]),"+f"(d[63]),"+f"(d[64]),"+f"(d[65]),"+f"(d[66]),"+f"(d[67]),"+f"(d[68]),"+f"(d[69]),"+f"(d[70]),"+f"(d[71]),"+f"(d[72]),"+f"(d[73]),"+f"(d[74]),"+f"(d[75]),"+f"(d[76]),"+f"(d[77]),"+f"(d[78]),"+f"(d[79]),"+f"(d[80]),"+f"(d[81]),"+f"(d[82]),"+f"(d[83]),"+f"(d[84]),"+f"(d[85]),"+f"(d[86]),"+f"(d[87]),"+f"(d[88]),"+f"(d[89]),"+f"(d[90]),"+f"(d[91]),"+f"(d[92]),"+f"(d[93]),"+f"(d[94]),"+f"(d[95]),"+f"(d[96]),"+f"(d[97]),"+f"(d[98]),"+f"(d[99]),"+f"(d[100]),"+f"(d[101]),"+f"(d[102]),"+f"(d[103]),"+f"(d[104]),"+f"(d[105]),"+f"(d[106]),"+f"(d[107]),"+f"(d[108]),"+f"(d[109]),"+f"(d[110]),"+f"(d[111]),"+f"(d[112]),"+f"(d[113]),"+f"(d[114]),"+f"(d[115]),"+f"(d[116]),"+f"(d[117]),"+f"(d[118]),"+f"(d[119]),"+f"(d[120]),"+f"(d[121]),"+f"(d[122]),"+f"(d[123]),"+f"(d[124]),"+f"(d[125]),"+f"(d[126]),"+f"(d[127])
    : "r"(a0), "r"(a1), "r"(a2), "r"(a3), "r"(db), "r"(sd), "n"((uint32_t)(CB >> 32)));
}
template<uint64_t CA, uint64_t CB> __device__ __forceinline__ void wgmma_ss_128(float* d, uint32_t da, uint32_t db, int sd) {
  asm volatile("{\n.reg .pred p;\n.reg .b64 a, b;\nsetp.ne.b32 p, %66, 0;\nmov.b64 a, {%64, %67};\nmov.b64 b, {%65, %68};\n"
    "wgmma.mma_async.sync.aligned.m64n128k16.f32.bf16.bf16 {%0,%1,%2,%3,%4,%5,%6,%7,%8,%9,%10,%11,%12,%13,%14,%15,%16,%17,%18,%19,%20,%21,%22,%23,%24,%25,%26,%27,%28,%29,%30,%31,%32,%33,%34,%35,%36,%37,%38,%39,%40,%41,%42,%43,%44,%45,%46,%47,%48,%49,%50,%51,%52,%53,%54,%55,%56,%57,%58,%59,%60,%61,%62,%63}, a, b, p, 1, 1, 0, 1;\n}\n"
    : "+f"(d[0]),"+f"(d[1]),"+f"(d[2]),"+f"(d[3]),"+f"(d[4]),"+f"(d[5]),"+f"(d[6]),"+f"(d[7]),"+f"(d[8]),"+f"(d[9]),"+f"(d[10]),"+f"(d[11]),"+f"(d[12]),"+f"(d[13]),"+f"(d[14]),"+f"(d[15]),"+f"(d[16]),"+f"(d[17]),"+f"(d[18]),"+f"(d[19]),"+f"(d[20]),"+f"(d[21]),"+f"(d[22]),"+f"(d[23]),"+f"(d[24]),"+f"(d[25]),"+f"(d[26]),"+f"(d[27]),"+f"(d[28]),"+f"(d[29]),"+f"(d[30]),"+f"(d[31]),"+f"(d[32]),"+f"(d[33]),"+f"(d[34]),"+f"(d[35]),"+f"(d[36]),"+f"(d[37]),"+f"(d[38]),"+f"(d[39]),"+f"(d[40]),"+f"(d[41]),"+f"(d[42]),"+f"(d[43]),"+f"(d[44]),"+f"(d[45]),"+f"(d[46]),"+f"(d[47]),"+f"(d[48]),"+f"(d[49]),"+f"(d[50]),"+f"(d[51]),"+f"(d[52]),"+f"(d[53]),"+f"(d[54]),"+f"(d[55]),"+f"(d[56]),"+f"(d[57]),"+f"(d[58]),"+f"(d[59]),"+f"(d[60]),"+f"(d[61]),"+f"(d[62]),"+f"(d[63])
    : "r"(da), "r"(db), "r"(sd), "n"((uint32_t)(CA >> 32)), "n"((uint32_t)(CB >> 32)));
}
template<uint64_t CA, uint64_t CB> __device__ __forceinline__ void wgmma_ss_64(float* d, uint32_t da, uint32_t db, int sd) {
  asm volatile("{\n.reg .pred p;\n.reg .b64 a, b;\nsetp.ne.b32 p, %34, 0;\nmov.b64 a, {%32, %35};\nmov.b64 b, {%33, %36};\n"
    "wgmma.mma_async.sync.aligned.m64n64k16.f32.bf16.bf16 {%0,%1,%2,%3,%4,%5,%6,%7,%8,%9,%10,%11,%12,%13,%14,%15,%16,%17,%18,%19,%20,%21,%22,%23,%24,%25,%26,%27,%28,%29,%30,%31}, a, b, p, 1, 1, 0, 1;\n}\n"
    : "+f"(d[0]),"+f"(d[1]),"+f"(d[2]),"+f"(d[3]),"+f"(d[4]),"+f"(d[5]),"+f"(d[6]),"+f"(d[7]),"+f"(d[8]),"+f"(d[9]),"+f"(d[10]),"+f"(d[11]),"+f"(d[12]),"+f"(d[13]),"+f"(d[14]),"+f"(d[15]),"+f"(d[16]),"+f"(d[17]),"+f"(d[18]),"+f"(d[19]),"+f"(d[20]),"+f"(d[21]),"+f"(d[22]),"+f"(d[23]),"+f"(d[24]),"+f"(d[25]),"+f"(d[26]),"+f"(d[27]),"+f"(d[28]),"+f"(d[29]),"+f"(d[30]),"+f"(d[31])
    : "r"(da), "r"(db), "r"(sd), "n"((uint32_t)(CA >> 32)), "n"((uint32_t)(CB >> 32)));
}
template<uint64_t CA, uint64_t CB> __device__ __forceinline__ void wgmma_ss_112(float* d, uint32_t da, uint32_t db, int sd) {
  asm volatile("{\n.reg .pred p;\n.reg .b64 a, b;\nsetp.ne.b32 p, %58, 0;\nmov.b64 a, {%56, %59};\nmov.b64 b, {%57, %60};\n"
    "wgmma.mma_async.sync.aligned.m64n112k16.f32.bf16.bf16 {%0,%1,%2,%3,%4,%5,%6,%7,%8,%9,%10,%11,%12,%13,%14,%15,%16,%17,%18,%19,%20,%21,%22,%23,%24,%25,%26,%27,%28,%29,%30,%31,%32,%33,%34,%35,%36,%37,%38,%39,%40,%41,%42,%43,%44,%45,%46,%47,%48,%49,%50,%51,%52,%53,%54,%55}, a, b, p, 1, 1, 0, 1;\n}\n"
    : "+f"(d[0]),"+f"(d[1]),"+f"(d[2]),"+f"(d[3]),"+f"(d[4]),"+f"(d[5]),"+f"(d[6]),"+f"(d[7]),"+f"(d[8]),"+f"(d[9]),"+f"(d[10]),"+f"(d[11]),"+f"(d[12]),"+f"(d[13]),"+f"(d[14]),"+f"(d[15]),"+f"(d[16]),"+f"(d[17]),"+f"(d[18]),"+f"(d[19]),"+f"(d[20]),"+f"(d[21]),"+f"(d[22]),"+f"(d[23]),"+f"(d[24]),"+f"(d[25]),"+f"(d[26]),"+f"(d[27]),"+f"(d[28]),"+f"(d[29]),"+f"(d[30]),"+f"(d[31]),"+f"(d[32]),"+f"(d[33]),"+f"(d[34]),"+f"(d[35]),"+f"(d[36]),"+f"(d[37]),"+f"(d[38]),"+f"(d[39]),"+f"(d[40]),"+f"(d[41]),"+f"(d[42]),"+f"(d[43]),"+f"(d[44]),"+f"(d[45]),"+f"(d[46]),"+f"(d[47]),"+f"(d[48]),"+f"(d[49]),"+f"(d[50]),"+f"(d[51]),"+f"(d[52]),"+f"(d[53]),"+f"(d[54]),"+f"(d[55])
    : "r"(da), "r"(db), "r"(sd), "n"((uint32_t)(CA >> 32)), "n"((uint32_t)(CB >> 32)));
}
template<uint64_t CB> __device__ __forceinline__ void wgmma_rs_112(float* d, uint32_t a0, uint32_t a1, uint32_t a2, uint32_t a3, uint32_t db, int sd) {
  asm volatile("{\n.reg .pred p;\n.reg .b64 b;\nsetp.ne.b32 p, %61, 0;\nmov.b64 b, {%60, %62};\n"
    "wgmma.mma_async.sync.aligned.m64n112k16.f32.bf16.bf16 {%0,%1,%2,%3,%4,%5,%6,%7,%8,%9,%10,%11,%12,%13,%14,%15,%16,%17,%18,%19,%20,%21,%22,%23,%24,%25,%26,%27,%28,%29,%30,%31,%32,%33,%34,%35,%36,%37,%38,%39,%40,%41,%42,%43,%44,%45,%46,%47,%48,%49,%50,%51,%52,%53,%54,%55}, {%56,%57,%58,%59}, b, p, 1, 1, 1;\n}\n"
    : "+f"(d[0]),"+f"(d[1]),"+f"(d[2]),"+f"(d[3]),"+f"(d[4]),"+f"(d[5]),"+f"(d[6]),"+f"(d[7]),"+f"(d[8]),"+f"(d[9]),"+f"(d[10]),"+f"(d[11]),"+f"(d[12]),"+f"(d[13]),"+f"(d[14]),"+f"(d[15]),"+f"(d[16]),"+f"(d[17]),"+f"(d[18]),"+f"(d[19]),"+f"(d[20]),"+f"(d[21]),"+f"(d[22]),"+f"(d[23]),"+f"(d[24]),"+f"(d[25]),"+f"(d[26]),"+f"(d[27]),"+f"(d[28]),"+f"(d[29]),"+f"(d[30]),"+f"(d[31]),"+f"(d[32]),"+f"(d[33]),"+f"(d[34]),"+f"(d[35]),"+f"(d[36]),"+f"(d[37]),"+f"(d[38]),"+f"(d[39]),"+f"(d[40]),"+f"(d[41]),"+f"(d[42]),"+f"(d[43]),"+f"(d[44]),"+f"(d[45]),"+f"(d[46]),"+f"(d[47]),"+f"(d[48]),"+f"(d[49]),"+f"(d[50]),"+f"(d[51]),"+f"(d[52]),"+f"(d[53]),"+f"(d[54]),"+f"(d[55])
    : "r"(a0), "r"(a1), "r"(a2), "r"(a3), "r"(db), "r"(sd), "n"((uint32_t)(CB >> 32)));
}

constexpr int DM = 448;
constexpr int NCTA = 128;
#define MAPPING 1
#define GRID 132
#define PINGPONG 0
#define WIN 6
#define WIN_END 25
#define UNR_G2 21
#define UNR_B 7
#define UNR_C 7
constexpr int kG2 = UNR_G2, kB = UNR_B, kC = UNR_C;
#define PACE 1
#define PACE_END 6
#define MAP_S 4
constexpr int SPIN_LIMIT = 1 << 22;

constexpr uint32_t OFF_X = 0, OFF_Y = 114688, OFF_MISC = 229376, SMEM_BYTES = 232448;
constexpr uint32_t Y_VR = 0, Y_K = 28672, Y_KOWN = 57344, Y_VOWN = 71680, Y_Q = 86016;
constexpr uint32_t HALF = 57344;
constexpr uint32_t M_BAR = OFF_MISC;
constexpr uint32_t M_ST = OFF_MISC + 512;
constexpr uint32_t M_G = OFF_MISC + 2304;
constexpr uint32_t M_EPOCH = OFF_MISC + 3040;
enum { B_XFULL = 0, B_FULLK = 7, B_FULLV = 8, B_FULLQ, B_KRFULL, B_VRFULL, B_WOFULL, B_XCH, B_FULL = 16, B_MOD1 = 28, B_MOD2, B_WMFULL,
       B_EMPTY = 32, B_XFREE = B_EMPTY + 12, B_GEMV, B_PEER,
       B_PUB = 47,
       B_WMFREE = 56, B_HRDY, B_GFULL = B_HRDY + 3, B_DONE = 31 };
constexpr uint32_t X_STAT = 49152;

__device__ uint32_t g_ticket;
__device__ __align__(128) uint32_t g_mod[8 * 6 * DM];
__device__ __align__(128) uint32_t g_flag[144 * 128];
__device__ __align__(128) uint32_t g_kv[17 * 8 * 2 * 3584];
__device__ __align__(128) uint32_t g_ox[3 * 34 * 14336];
#define g_o g_ox
#define g_x1 (g_ox + 34 * 14336)
__device__ __align__(128) float2 g_st[2 * 34 * 8 * 64];
__device__ __align__(128) uint32_t g_wd[56 * 4 * 1792];
__device__ __align__(128) uint32_t g_h2[17 * 224 * 512];
#define PROFH(id)
#define PROFH1(id)
#define PROFC(id)

struct alignas(64) Params {
    CUtensorMap wm, xm, qkv, wo, ga, ua, gb, ub, gc, uc, dn;
    const bf16 *x, *c, *wqkv, *wmod, *wg, *wu, *wd, *wop;
    bf16* out;
    uint32_t zero;
};

__device__ __forceinline__ void mbar_init(uint32_t bar, int cnt) { asm volatile("mbarrier.init.shared::cta.b64 [%0], %1;" ::"r"(bar), "r"(cnt) : "memory"); }
__device__ __forceinline__ void mbar_expect_tx(uint32_t bar, uint32_t bytes) { asm volatile("mbarrier.arrive.expect_tx.shared::cta.b64 _, [%0], %1;" ::"r"(bar), "r"(bytes) : "memory"); }
__device__ __forceinline__ void mbar_arrive(uint32_t bar) { asm volatile("mbarrier.arrive.shared::cta.b64 _, [%0];" ::"r"(bar) : "memory"); }
__device__ __forceinline__ void mbar_wait(uint32_t bar, uint32_t parity) {
    uint32_t ok; int n = 0;
    do {
        asm volatile("{\n.reg .pred p;\nmbarrier.try_wait.parity.shared::cta.b64 p, [%1], %2;\nselp.u32 %0, 1, 0, p;\n}" : "=r"(ok) : "r"(bar), "r"(parity) : "memory");
        if (++n > SPIN_LIMIT) __trap();
    } while (!ok);
}
__device__ __forceinline__ void mbar_wait_c(uint32_t bar, uint32_t parity) {
    asm volatile("{\n.reg .pred p;\nWL:\nmbarrier.try_wait.parity.shared::cta.b64 p, [%0], %1;\n@!p bra WL;\n}" ::"r"(bar), "r"(parity) : "memory");
}
__device__ __forceinline__ void mbar_wait_cluster(uint32_t bar, uint32_t parity) {
    uint32_t ok; int n = 0;
    do {
        asm volatile("{\n.reg .pred p;\nmbarrier.try_wait.parity.acquire.cluster.shared::cta.b64 p, [%1], %2;\nselp.u32 %0, 1, 0, p;\n}" : "=r"(ok) : "r"(bar), "r"(parity) : "memory");
        if (++n > SPIN_LIMIT) __trap();
    } while (!ok);
}
__device__ __forceinline__ void warp_arrive(uint32_t bar) {
    __syncwarp();
    asm volatile("{\n.reg .pred p;\nelect.sync _|p, 0xffffffff;\n@p mbarrier.arrive.shared::cta.b64 _, [%0];\n}" ::"r"(bar) : "memory");
}
__device__ __forceinline__ int opaque(int v) { return __shfl_sync(~0u, v, 0); }
__device__ __forceinline__ int fresh_tid() { int v; asm volatile("mov.u32 %0, %%tid.x;" : "=r"(v)); return v; }
__device__ __forceinline__ void bar_sync(int id, int n) { asm volatile("bar.sync %0, %1;" ::"r"(id), "r"(n) : "memory"); }
__device__ __forceinline__ void bar_arrive(int id, int n) { asm volatile("bar.arrive %0, %1;" ::"r"(id), "r"(n) : "memory"); }
__device__ __forceinline__ void fence_async_smem() { asm volatile("fence.proxy.async.shared::cta;" ::: "memory"); }
__device__ __forceinline__ void fence_async_global() { asm volatile("fence.proxy.async.global;" ::: "memory"); }
__device__ __forceinline__ void fence_gpu() { asm volatile("fence.release.gpu;" ::: "memory"); }
__device__ __forceinline__ void tma3(uint32_t dst, const CUtensorMap* m, int c0, int c1, int c2, uint32_t bar) {
    asm volatile("cp.async.bulk.tensor.3d.shared::cluster.global.mbarrier::complete_tx::bytes [%0], [%1, {%3, %4, %5}], [%2];"
                 ::"r"(dst), "l"(m), "r"(bar), "r"(c0), "r"(c1), "r"(c2) : "memory");
}
__device__ __forceinline__ void bulk_load(uint32_t dst, const void* src, uint32_t bytes, uint32_t bar) {
    asm volatile("cp.async.bulk.shared::cluster.global.mbarrier::complete_tx::bytes [%0], [%1], %2, [%3];" ::"r"(dst), "l"(src), "r"(bytes), "r"(bar) : "memory");
}
__device__ __forceinline__ void expect_e(uint32_t bar, uint32_t bytes) {
    asm volatile("{\n.reg .pred p;\nelect.sync _|p, 0xffffffff;\n@p mbarrier.arrive.expect_tx.shared::cta.b64 _, [%0], %1;\n}" ::"r"(bar), "r"(bytes) : "memory");
}
__device__ __forceinline__ void tma3_e(uint32_t dst, const CUtensorMap* m, int c0, int c1, int c2, uint32_t bar) {
    asm volatile("{\n.reg .pred p;\nelect.sync _|p, 0xffffffff;\n@p cp.async.bulk.tensor.3d.shared::cluster.global.mbarrier::complete_tx::bytes [%0], [%1, {%3, %4, %5}], [%2];\n}"
                 ::"r"(dst), "l"(m), "r"(bar), "r"(c0), "r"(c1), "r"(c2) : "memory");
}
__device__ __forceinline__ void bulk_e(uint32_t dst, const void* src, uint32_t bytes, uint32_t bar) {
    asm volatile("{\n.reg .pred p;\nelect.sync _|p, 0xffffffff;\n@p cp.async.bulk.shared::cluster.global.mbarrier::complete_tx::bytes [%0], [%1], %2, [%3];\n}"
                 ::"r"(dst), "l"(src), "r"(bytes), "r"(bar) : "memory");
}
__device__ __forceinline__ void init_e(uint32_t bar, int cnt) {
    asm volatile("{\n.reg .pred p;\nelect.sync _|p, 0xffffffff;\n@p mbarrier.init.shared::cta.b64 [%0], %1;\n}" ::"r"(bar), "r"(cnt) : "memory");
}
__device__ __forceinline__ void l2_prefetch_e(const void* src, uint32_t bytes) {
    asm volatile("{\n.reg .pred p;\nelect.sync _|p, 0xffffffff;\n@p cp.async.bulk.prefetch.L2.global [%0], %1;\n}" ::"l"(src), "r"(bytes) : "memory");
}
__device__ __forceinline__ uint32_t ld_relaxed(const uint32_t* p) { uint32_t v; asm volatile("ld.relaxed.gpu.global.u32 %0, [%1];" : "=r"(v) : "l"(p) : "memory"); return v; }
__device__ __forceinline__ void st_relaxed(uint32_t* p, uint32_t v) { asm volatile("st.relaxed.gpu.global.u32 [%0], %1;" ::"l"(p), "r"(v) : "memory"); }
__device__ __forceinline__ uint4 ld_relaxed4(const uint4* p) { uint4 v; asm volatile("ld.relaxed.gpu.global.v4.u32 {%0,%1,%2,%3}, [%4];" : "=r"(v.x), "=r"(v.y), "=r"(v.z), "=r"(v.w) : "l"(p) : "memory"); return v; }
__device__ __forceinline__ void st_relaxed4(uint4* p, uint4 v) { asm volatile("st.relaxed.gpu.global.v4.u32 [%0], {%1,%2,%3,%4};" ::"l"(p), "r"(v.x), "r"(v.y), "r"(v.z), "r"(v.w) : "memory"); }
__device__ __forceinline__ uint4 ldg_nc4(const void* p) { uint4 v; asm volatile("ld.global.nc.L1::no_allocate.v4.u32 {%0,%1,%2,%3}, [%4];" : "=r"(v.x), "=r"(v.y), "=r"(v.z), "=r"(v.w) : "l"(p)); return v; }
__device__ __forceinline__ uint32_t ldg_nc(const void* p) { uint32_t v; asm volatile("ld.global.nc.u32 %0, [%1];" : "=r"(v) : "l"(p)); return v; }
__device__ __forceinline__ uint32_t ld_acquire(const uint32_t* p) { uint32_t v; asm volatile("ld.acquire.gpu.global.u32 %0, [%1];" : "=r"(v) : "l"(p) : "memory"); return v; }
__device__ __forceinline__ uint4 lds4(uint32_t a) { uint4 v; asm volatile("ld.shared.v4.u32 {%0,%1,%2,%3}, [%4];" : "=r"(v.x), "=r"(v.y), "=r"(v.z), "=r"(v.w) : "r"(a) : "memory"); return v; }
__device__ __forceinline__ float2 lds2f(uint32_t a) { float2 v; asm volatile("ld.shared.v2.f32 {%0,%1}, [%2];" : "=f"(v.x), "=f"(v.y) : "r"(a) : "memory"); return v; }
__device__ __forceinline__ uint32_t lds1(uint32_t a) { uint32_t v; asm volatile("ld.shared.u32 %0, [%1];" : "=r"(v) : "r"(a) : "memory"); return v; }
__device__ __forceinline__ void sts4(uint32_t a, uint4 v) { asm volatile("st.shared.v4.u32 [%0], {%1,%2,%3,%4};" ::"r"(a), "r"(v.x), "r"(v.y), "r"(v.z), "r"(v.w) : "memory"); }
__device__ __forceinline__ void sts2(uint32_t a, uint32_t x, uint32_t y) { asm volatile("st.shared.v2.u32 [%0], {%1,%2};" ::"r"(a), "r"(x), "r"(y) : "memory"); }
__device__ __forceinline__ void sts1(uint32_t a, uint32_t v) { asm volatile("st.shared.u32 [%0], %1;" ::"r"(a), "r"(v) : "memory"); }
__device__ __forceinline__ void stsm4(uint32_t a, uint32_t r0, uint32_t r1, uint32_t r2, uint32_t r3) {
    asm volatile("stmatrix.sync.aligned.m8n8.x4.shared.b16 [%0], {%1,%2,%3,%4};" ::"r"(a), "r"(r0), "r"(r1), "r"(r2), "r"(r3));
}
__device__ __forceinline__ uint32_t pack2(float lo, float hi) { uint32_t r; asm("cvt.rn.bf16x2.f32 %0, %1, %2;" : "=r"(r) : "f"(hi), "f"(lo)); return r; }
__device__ __forceinline__ uint32_t pack2_relu(float lo, float hi) { uint32_t r; asm("cvt.rn.relu.bf16x2.f32 %0, %1, %2;" : "=r"(r) : "f"(hi), "f"(lo)); return r; }
__device__ __forceinline__ uint32_t hfma2(uint32_t a, uint32_t b, uint32_t c) { uint32_t r; asm("fma.rn.bf16x2 %0, %1, %2, %3;" : "=r"(r) : "r"(a), "r"(b), "r"(c)); return r; }
__device__ __forceinline__ uint32_t hmul2(uint32_t a, uint32_t b) { uint32_t r; asm("mul.rn.bf16x2 %0, %1, %2;" : "=r"(r) : "r"(a), "r"(b)); return r; }
__device__ __forceinline__ float bf_lo(uint32_t v) { return __uint_as_float(v << 16); }
__device__ __forceinline__ float bf_hi(uint32_t v) { return __uint_as_float(v & 0xFFFF0000u); }
__device__ __forceinline__ float bf_round(float v) { return bf_lo(pack2(v, 0.f)); }
__device__ __forceinline__ float ex2(float x) { float r; asm("ex2.approx.ftz.f32 %0, %1;" : "=f"(r) : "f"(x)); return r; }
__device__ __forceinline__ void mma16816(float* d, uint32_t a0, uint32_t a1, uint32_t a2, uint32_t a3, uint32_t b0, uint32_t b1) {
    asm("mma.sync.aligned.m16n8k16.row.col.f32.bf16.bf16.f32 {%0,%1,%2,%3}, {%4,%5,%6,%7}, {%8,%9}, {%0,%1,%2,%3};"
        : "+f"(d[0]), "+f"(d[1]), "+f"(d[2]), "+f"(d[3]) : "r"(a0), "r"(a1), "r"(a2), "r"(a3), "r"(b0), "r"(b1));
}
__device__ __forceinline__ void mma16816_first(float* d, uint32_t a0, uint32_t a1, uint32_t a2, uint32_t a3, uint32_t b0, uint32_t b1) {
    asm volatile("mma.sync.aligned.m16n8k16.row.col.f32.bf16.bf16.f32 {%0,%1,%2,%3}, {%4,%5,%6,%7}, {%8,%9}, {%10,%10,%10,%10};"
        : "=f"(d[0]), "=f"(d[1]), "=f"(d[2]), "=f"(d[3]) : "r"(a0), "r"(a1), "r"(a2), "r"(a3), "r"(b0), "r"(b1), "f"(0.f));
}
__device__ __forceinline__ void mma16816_v(float* d, uint32_t a0, uint32_t a1, uint32_t a2, uint32_t a3, uint32_t b0, uint32_t b1) {
    asm volatile("mma.sync.aligned.m16n8k16.row.col.f32.bf16.bf16.f32 {%0,%1,%2,%3}, {%4,%5,%6,%7}, {%8,%9}, {%0,%1,%2,%3};"
        : "+f"(d[0]), "+f"(d[1]), "+f"(d[2]), "+f"(d[3]) : "r"(a0), "r"(a1), "r"(a2), "r"(a3), "r"(b0), "r"(b1));
}
__device__ __forceinline__ void mma1688(float* d, uint32_t a0, uint32_t a1, uint32_t b0) {
    asm("mma.sync.aligned.m16n8k8.row.col.f32.bf16.bf16.f32 {%0,%1,%2,%3}, {%4,%5}, {%6}, {%0,%1,%2,%3};"
        : "+f"(d[0]), "+f"(d[1]), "+f"(d[2]), "+f"(d[3]) : "r"(a0), "r"(a1), "r"(b0));
}
__device__ __forceinline__ void ldsm4(uint32_t a, uint32_t* r) {
    asm volatile("ldmatrix.sync.aligned.m8n8.x4.shared.b16 {%0,%1,%2,%3}, [%4];" : "=r"(r[0]), "=r"(r[1]), "=r"(r[2]), "=r"(r[3]) : "r"(a));
}
__device__ __forceinline__ void ldsm4t(uint32_t a, uint32_t* r) {
    asm volatile("ldmatrix.sync.aligned.m8n8.x4.trans.shared.b16 {%0,%1,%2,%3}, [%4];" : "=r"(r[0]), "=r"(r[1]), "=r"(r[2]), "=r"(r[3]) : "r"(a));
}
__device__ __forceinline__ float rcp(float x) { float r; asm("rcp.approx.ftz.f32 %0, %1;" : "=f"(r) : "f"(x)); return r; }
__device__ __forceinline__ uint2 ld_relaxed2(const void* p) { uint2 v; asm volatile("ld.relaxed.gpu.global.v2.u32 {%0,%1}, [%2];" : "=r"(v.x), "=r"(v.y) : "l"(p) : "memory"); return v; }
__device__ __forceinline__ void st_relaxed2(void* p, uint32_t x, uint32_t y) { asm volatile("st.relaxed.gpu.global.v2.u32 [%0], {%1,%2};" ::"l"(p), "r"(max(x, 1u)), "r"(max(y, 1u)) : "memory"); }
__host__ __device__ constexpr uint64_t dconst(uint32_t lbo, uint32_t sbo, uint32_t swz) {
    return ((uint64_t)(lbo >> 4) << 16) | ((uint64_t)(sbo >> 4) << 32) | ((uint64_t)swz << 62);
}
__device__ __forceinline__ uint32_t mkdesc(uint32_t addr, uint64_t c) { return (uint32_t)c | ((addr & 0x3FFFF) >> 4); }
#define WG_FENCE() asm volatile("wgmma.fence.sync.aligned;" ::: "memory")
#define WG_COMMIT() asm volatile("wgmma.commit_group.sync.aligned;" ::: "memory")
#define WG_WAIT(n) asm volatile("wgmma.wait_group.sync.aligned %0;" ::"n"(n) : "memory")
template <int N> __device__ __forceinline__ void reg_fence(float* d) {
#pragma unroll
    for (int i = 0; i < N; i++) asm volatile("" : "+f"(d[i])::"memory");
}
template <int N> __device__ __forceinline__ void reg_def(float* d) {
#pragma unroll
    for (int i = 0; i < N; i++) asm volatile("" : "=f"(d[i]));
}
template <int N> __device__ __forceinline__ void reg_def(uint32_t* d) {
#pragma unroll
    for (int i = 0; i < N; i++) asm volatile("" : "=r"(d[i]));
}
__device__ __forceinline__ bool is_unset(uint4 v) { return min(min(v.x, v.y), min(v.z, v.w)) == 0u; }
__device__ __forceinline__ uint4 nz4(uint32_t a, uint32_t b, uint32_t c, uint32_t d) { return make_uint4(max(a, 1u), max(b, 1u), max(c, 1u), max(d, 1u)); }
__device__ __forceinline__ void wait_flags(const uint32_t* p, uint32_t target, uint32_t mask) {
    int n = 0;
    while (~__ballot_sync(~0u, (int)(ld_relaxed(p) - target) >= 0) & mask) { if (++n > SPIN_LIMIT) __trap(); }
    asm volatile("fence.acquire.gpu;" ::: "memory");
}
__device__ __forceinline__ float silu_bf(uint32_t cbits) {
    const float c = __uint_as_float(cbits << 16);
    return bf_round(__fdividef(c, 1.f + fminf(ex2(-1.4426950408889634f * c), 1e30f)));
}
__device__ __forceinline__ void gemv_part(uint32_t wmbuf, int npanel, int wp, int lane) {
    const uint32_t wa = wmbuf + wp * 512 + (8 * (lane >> 4) + (lane & 7)) * 32 + ((lane >> 3) & 1) * 16;
    uint2 B[4];
#pragma unroll
    for (int i = 0; i < 4; i++) { const float2 v = lds2f(wmbuf + 28672 + (wp + 8 * i) * 32 + (lane & 3) * 8); B[i] = make_uint2(__float_as_uint(v.x), __float_as_uint(v.y)); }
#pragma unroll 1
    for (int pn = 0; pn < npanel; pn++) {
        float d[4] = {};
        uint32_t A[16];
#pragma unroll
        for (int i = 0; i < 4; i++) ldsm4t(wa + pn * 14336 + (i < 3 || wp < 4 ? i : 0) * 4096, A + 4 * i);
#pragma unroll
        for (int i = 0; i < 4; i++) mma16816(d, A[4 * i], A[4 * i + 1], A[4 * i + 2], A[4 * i + 3], B[i].x, B[i].y);
        if ((lane & 3) == 0) {
            sts1(wmbuf + 29696 + (wp * 32 + pn * 16 + (lane >> 2)) * 4, __float_as_uint(d[0]));
            sts1(wmbuf + 29696 + (wp * 32 + pn * 16 + 8 + (lane >> 2)) * 4, __float_as_uint(d[2]));
        }
    }
}
__device__ __forceinline__ int pass_f(int fs, int ps) { return 224 * fs + ((fs & 1) ? (ps == 0 ? 96 : ps == 1 ? 32 : 0) : (ps == 0 ? 0 : ps == 1 ? 128 : 192)); }
__device__ __forceinline__ constexpr uint32_t slot_off(int l) { return (l < 3 || l > 6 ? l : l == 6 ? 3 : l + 1) * 16384; }
__device__ __forceinline__ void ln_coeffs(float mean, float msq, uint32_t& r2, uint32_t& n2) {
    const float rs = bf_round(rsqrtf(fmaxf(msq - mean * mean, 0.f) + 1e-5f));
    r2 = pack2(rs, rs);
    n2 = pack2(-mean * rs, -mean * rs);
}

#define LOADW bulk_e(dst, g_wd + (size_t)((f >> 5) * 4 + nq) * 1792, 7168, bar);
template <int sec> __device__ __forceinline__ void ring_loader(const Params& p, uint32_t sb_, int r_, int j_, int lane) {
    const uint32_t sb = opaque(sb_);
    const int r = opaque(r_), j = opaque(j_), nq = j >> 1, fs = 4 * (j & 1) + nq;
    const int fa = pass_f(fs, 0), fb = pass_f(fs, 1), fc = pass_f(fs, 2);
#define BAR(i) (sb + M_BAR + 8 * (i))
#define kh (j & 1)
            int sl = 0;
            mbar_wait(BAR(B_PUB + 2), 0);
            wait_flags(g_flag + (8 * r + j) * 128 + 96 + lane, lds1(sb + M_EPOCH) + 1, 0xFFFFu);
            fence_async_global();
#pragma unroll 1
            for (int s = 0; s < 28; s++) {
                if (s >= PACE && s < PACE_END) mbar_wait(BAR(B_FULL + s - PACE), 0);
                const int ps = s < 14 ? 0 : s < 21 ? 1 : 2;
                const uint32_t half = ps < 2 ? 8192 : 4096;
                mbar_wait(BAR(B_EMPTY + sl), (s >= 7 && s < 14) || s >= 21);
                expect_e(BAR(B_FULL + sl), half);
                tma3_e(sb + slot_off(sl) + sec * half, &p.ga + 2 * ps + sec, 0, ps ? 64 * sl : 32 * s, ps == 0 ? fa >> 6 : ps == 1 ? fb >> 6 : fc >> 5, BAR(B_FULL + sl));
                sl = sl == 6 ? 0 : sl + 1;
            }
            if (!sec) PROFH(3);
#pragma unroll 1
            for (int e = 0; e < 4; e++) {
                const uint32_t dst = sb + slot_off(e) + sec * 8192, bar = BAR(B_FULL + e);
                const int f = (e < 2 ? fa + 64 * e : e == 2 ? fb : fc) + 32 * sec;
                mbar_wait(BAR(B_EMPTY + e), 0);
                expect_e(bar, e == 3 && sec ? 0 : 7168);
                if (!(e == 3 && sec)) { LOADW }
            }
            sl = 4;
            int e = 4;
#pragma unroll 1
            for (int grp = 0; grp < 9; grp++) {
                const int ps = grp >= 6 ? 2 : grp >= 3 ? 1 : 0;
                int sidx = grp - 3 * ps;
                if (sec && sidx == 0) { mbar_wait(BAR(B_HRDY + ps), 0); fence_async_global(); }
                sidx += sidx >= nq;
                int f = pass_f(4 * kh + sidx, ps);
#pragma unroll 1
                for (int k = 4 >> ps; k > 0; k--, e++, f += 32) {
                    const uint32_t dst = sb + slot_off(sl), bar = BAR(B_FULL + sl);
                    mbar_wait(BAR(B_EMPTY + sl), e >= 12 && e < 24);
                    if (e < WIN_END && e >= WIN) mbar_wait(BAR(B_FULL + (sl >= WIN ? sl - WIN : sl + 12 - WIN)), e - WIN >= 12);
                    expect_e(bar, sec ? 8192 : 7168);
                    if (!sec) { LOADW }
                    else bulk_e(dst + 8192, g_h2 + (size_t)r * (224 * 512) + f * 64, 8192, bar);
                    sl = sl == 11 ? 0 : sl + 1;
                }
            }
            if (!sec) PROFH(4);
}

__global__ void __cluster_dims__(2, 1, 1) __launch_bounds__(384, 1) fused_block_kernel(const __grid_constant__ Params p) {
    extern __shared__ __align__(1024) unsigned char smem[];
    const uint32_t sb = (uint32_t)__cvta_generic_to_shared(smem);
    const int tid = threadIdx.x, lane = tid & 31, warp = __shfl_sync(~0u, tid >> 5, 0);
    const int m = blockIdx.x >> 1;
    int r, nq;
    {
        int g, i;
        if (m < MAP_S) { g = m < 4 ? 15 : 16; i = m & 3; }
        else if (m < MAP_S + 32) { g = (m - MAP_S) & 7; i = (m - MAP_S) >> 3; }
        else if (m < MAP_S + 60) { i = (m - MAP_S - 32) / 7; g = 8 + (m - MAP_S - 32) - 7 * i; }
        else { g = 16; i = m & 3; }
        r = g; nq = i;
    }
    const int j = opaque(2 * nq + (blockIdx.x & 1)), b = 8 * r + j, fs = 4 * kh + nq;
    const uint32_t sc = r == 16;
    if (lane == 0 && warp < 9 && warp != 6 && warp != 7) {
        const int i0 = warp == 8 ? 0 : 8 + 8 * warp, cnt = warp == 0 || warp == 8 ? 1 : warp < 3 ? 2 : 8;
#pragma unroll
        for (int k = 0; k < 8; k++) if (i0 + k != B_WMFULL) mbar_init(BAR(i0 + k), cnt);
        asm volatile("fence.mbarrier_init.release.cluster;" ::: "memory");
        fence_async_smem();
    }

    if (warp < 8) {
        const int w = warp >> 2, wi = warp & 3;
#define COORDS const int t = fresh_tid() & 127, lane = t & 31, q = lane & 3, lr = lane >> 2, ra = 64 * w + 16 * wi + lr; \
        const uint32_t lx = (lane >> 4) ^ (lane & 7), mrow = (64 * w + 16 * wi + ((lane >> 3) & 1) * 8 + (lane & 7)) * 128; \
        (void)q; (void)lr; (void)ra; (void)lx; (void)mrow;
        const int sid = 2 * (j & 3) + w;
#define RUN(k) (!sc || sid == (k))
#define WAIT(i, par) mbar_wait_c(BAR(i), (par) | sc)
        constexpr uint64_t DB128 = dconst(4096, 1024, 1);
        bar_arrive(9, 384);
        bar_sync(0, 384);
        asm volatile("barrier.cluster.arrive.relaxed.aligned;" ::: "memory");
        asm volatile("setmaxnreg.inc.sync.aligned.u32 224;");
        PROFC(0);
        uint32_t xr[16];
        {
            COORDS
            uint32_t h[112];
            if (RUN(0)) {
                float ds[4] = {}, da[2][4] = {}, db[2][4] = {};
                const uint32_t ONE2 = 0x3F803F80u;
                if (kh == 0) { WAIT(B_WMFULL, 0); gemv_part(sb + OFF_Y + HALF, 1, warp, lane); warp_arrive(BAR(B_GEMV)); }
#pragma unroll
                for (int kb = 0; kb < 7; kb++) {
                    WAIT(B_XFULL + kb, 0);
#pragma unroll
                    for (int k4 = 0; k4 < 4; k4++) ldsm4(sb + OFF_X + mrow + kb * 16384 + (((2 * k4) ^ lx) << 4), h + 16 * kb + 4 * k4);
#pragma unroll
                    for (int k4 = 0; k4 < 4; k4++) {
                        const uint32_t* f = h + 16 * kb + 4 * k4;
                        mma16816(ds, f[0], f[1], f[2], f[3], ONE2, ONE2);
                        mma1688(da[0], f[0], f[1], f[0]); mma1688(db[0], f[0], f[1], f[1]);
                        mma1688(da[1], f[2], f[3], f[2]); mma1688(db[1], f[2], f[3], f[3]);
                    }
                }
#pragma unroll
                for (int i = 0; i < 4; i++) {
                    const int ch = 7 * j + 2 * i + (lane >> 4);
                    ldsm4(sb + OFF_X + mrow + (ch >> 3) * 16384 + (((ch ^ lane) & 7) << 4), xr + 4 * i);
                }
                warp_arrive(BAR(B_XFREE));
                float qa = (lr & 1) ? da[0][1] + da[1][1] : da[0][0] + da[1][0];
                float qb = (lr & 1) ? db[0][3] + db[1][3] : db[0][2] + db[1][2];
                const int src = (lane & ~3) | (lr >> 1);
                qa = __shfl_sync(~0u, qa, src);
                qb = __shfl_sync(~0u, qb, src);
                uint32_t ra2, na2, rb2, nb2;
                ln_coeffs(ds[0] * (1.f / DM), qa * (1.f / DM), ra2, na2);
                ln_coeffs(ds[2] * (1.f / DM), qb * (1.f / DM), rb2, nb2);
#pragma unroll
                for (int i = 0; i < 112; i += 2) { h[i] = hfma2(h[i], ra2, na2); h[i + 1] = hfma2(h[i + 1], rb2, nb2); }
                if (kh == 1) { WAIT(B_WMFULL, 0); gemv_part(sb + OFF_Y + HALF, 2, warp, lane); warp_arrive(BAR(B_GEMV)); }
            } else { reg_def<112>(h); reg_def<16>(xr); }
            PROFC(1);
            if (RUN(1)) {
                float ak[28], av[28], aq[28];
                uint32_t kp[14], vp[14];
                const uint32_t bk0 = mkdesc(sb + OFF_Y, DB128) + kh, bv0 = mkdesc(sb + OFF_Y + HALF, DB128) + kh, bq0 = mkdesc(sb + OFF_X, DB128) + kh;
                uint32_t* kvg = g_kv + (size_t)(b * 2) * 3584 + (8 * w + 2 * wi) * 224 + lane;
                WAIT(B_FULLK, 0);
                WAIT(B_MOD1, 0);
                PROFC(2);
                reg_def<28>(ak);
#pragma unroll
                for (int g4 = 0; g4 < 4; g4++) {
#pragma unroll
                    for (int ks = 7 * g4; ks < 7 * g4 + 7; ks++) {
                        const uint4 st = *(const uint4*)(smem + M_ST + ks * 64 + q * 16);
                        h[4 * ks] = hfma2(h[4 * ks], st.x, st.y); h[4 * ks + 1] = hfma2(h[4 * ks + 1], st.x, st.y);
                        h[4 * ks + 2] = hfma2(h[4 * ks + 2], st.z, st.w); h[4 * ks + 3] = hfma2(h[4 * ks + 3], st.z, st.w);
                    }
                    WG_FENCE();
#pragma unroll
                    for (int ks = 7 * g4; ks < 7 * g4 + 7; ks++) wgmma_rs_56<DB128>(ak, h[4 * ks], h[4 * ks + 1], h[4 * ks + 2], h[4 * ks + 3], bk0 + ks * 128, ks != 0);
                }
                WG_COMMIT();
                PROFC(3);
                WAIT(B_FULLV, 0);
                reg_def<28>(av);
                WG_FENCE();
#pragma unroll
                for (int ks = 0; ks < 8; ks++) wgmma_rs_56<DB128>(av, h[4 * ks], h[4 * ks + 1], h[4 * ks + 2], h[4 * ks + 3], bv0 + ks * 128, ks != 0);
                WG_COMMIT();
                WG_WAIT(1);
                reg_fence<28>(ak);
#pragma unroll
                for (int g = 0; g < 7; g++) {
                    kp[2 * g] = pack2(ak[4 * g], ak[4 * g + 1]); kp[2 * g + 1] = pack2(ak[4 * g + 2], ak[4 * g + 3]);
                    kvg[g * 32] = kp[2 * g]; kvg[224 + g * 32] = kp[2 * g + 1];
                }
                warp_arrive(BAR(B_PUB));
                PROFC(4);
                WG_FENCE();
#pragma unroll
                for (int ks = 8; ks < 28; ks++) wgmma_rs_56<DB128>(av, h[4 * ks], h[4 * ks + 1], h[4 * ks + 2], h[4 * ks + 3], bv0 + ks * 128, 1);
                WG_COMMIT();
                WAIT(B_FULLQ, 0);
                reg_def<28>(aq);
                WG_FENCE();
#pragma unroll
                for (int ks = 0; ks < 8; ks++) wgmma_rs_56<DB128>(aq, h[4 * ks], h[4 * ks + 1], h[4 * ks + 2], h[4 * ks + 3], bq0 + ks * 128, ks != 0);
                WG_COMMIT();
                WG_WAIT(1);
                reg_fence<28>(av);
#pragma unroll
                for (int g = 0; g < 7; g++) {
                    vp[2 * g] = pack2(av[4 * g], av[4 * g + 1]); vp[2 * g + 1] = pack2(av[4 * g + 2], av[4 * g + 3]);
                    kvg[3584 + g * 32] = vp[2 * g]; kvg[3584 + 224 + g * 32] = vp[2 * g + 1];
                }
                warp_arrive(BAR(B_PUB + 1));
                PROFC(5);
                WG_FENCE();
#pragma unroll
                for (int ks = 8; ks < 28; ks++) wgmma_rs_56<DB128>(aq, h[4 * ks], h[4 * ks + 1], h[4 * ks + 2], h[4 * ks + 3], bq0 + ks * 128, 1);
                WG_COMMIT();
                WAIT(B_PUB + 1, 0);
                const uint32_t ko = sb + OFF_Y + Y_KOWN + (8 * w + 2 * wi) * 896 + lane * 4;
                const uint32_t qo = sb + OFF_Y + Y_Q + (8 * w + 2 * wi) * 1024 + lane * 4;
#pragma unroll
                for (int g = 0; g < 7; g++) {
                    sts1(ko + g * 128, kp[2 * g]); sts1(ko + 896 + g * 128, kp[2 * g + 1]);
                    sts1(ko + (Y_VOWN - Y_KOWN) + g * 128, vp[2 * g]); sts1(ko + (Y_VOWN - Y_KOWN) + 896 + g * 128, vp[2 * g + 1]);
                }
                WG_WAIT(0);
                reg_fence<28>(aq);
                __syncwarp();
                if (lane < 3 && w == 1) mbar_arrive(BAR(B_EMPTY + lane));
#pragma unroll
                for (int g = 0; g < 7; g++) {
                    const uint32_t q0 = pack2(aq[4 * g], aq[4 * g + 1]), q1 = pack2(aq[4 * g + 2], aq[4 * g + 3]);
                    if (g == 3) {
                        sts1(qo + 3 * 128, q < 2 ? q0 : 0u); sts1(qo + 1024 + 3 * 128, q < 2 ? q1 : 0u);
                        sts1(qo + 4 * 128, q < 2 ? 0u : q0); sts1(qo + 1024 + 4 * 128, q < 2 ? 0u : q1);
                    } else {
                        const int ch = g < 3 ? g : g + 1;
                        sts1(qo + ch * 128, q0); sts1(qo + 1024 + ch * 128, q1);
                    }
                }
                if (!sc) bar_sync(3, 256);
            }
        }
        PROFC(6);
        WAIT(B_KRFULL, 0);
        PROFC(7);
        if (RUN(2)) {
#pragma unroll 1
            for (int hf = sc; hf < 2; hf++) {
                COORDS
                float s[136];
                float na = 0.f, nb = 0.f;
                const float CS = 0.18898223650461361f * 1.4426950408889634f;
                const int kg0 = 8 * hf + 2 * wi;
                const int pmin = 16 - 8 * r - 4 * hf - wi;
                const float NEG = __int_as_float(0xFF800000);
                {
                    uint32_t F[8];
                    const uint32_t qa = sb + OFF_Y + Y_Q + (kg0 + ((lane >> 3) & 1)) * 1024 + (4 * w + (lane >> 4)) * 128 + (lane & 7) * 16;
                    ldsm4(qa, F); ldsm4(qa + 256, F + 4);
                    uint32_t ka = sb + OFF_Y + Y_K + kg0 * 896 + (3 * w + (lane >> 3)) * 128 + (lane & 7) * 16;
#pragma unroll
                    for (int g = 0; g < 34; g++) {
                        uint32_t B[4];
                        if (g >= 12 && g % 4 == 0) ka += __float_as_uint(s[4 * (g - 12)]) & p.zero;
                        ldsm4(ka + g * 896, B);
                        mma16816_first(s + 4 * g, F[0], F[1], F[2], F[3], B[0], B[1]);
                        mma16816_v(s + 4 * g, F[4], F[5], F[6], F[7], B[2], B[3]);
                    }
                    const bool c0 = 2 * q > lr, c1 = 2 * q + 1 > lr;
                    if (!c0) { s[0] = NEG; s[6] = NEG; }
                    if (!c1) { s[1] = NEG; s[7] = NEG; }
                    s[2] = NEG; s[3] = NEG;
                    if (c0) { s[128] = NEG; s[134] = NEG; }
                    if (c1) { s[129] = NEG; s[135] = NEG; }
                    s[132] = NEG; s[133] = NEG;
                    float ma = NEG, mb = NEG;
#pragma unroll
                    for (int pp = 0; pp < 17; pp++) {
                        const float* e = s + 8 * pp;
                        const float bias = pp < pmin ? NEG : 0.f;
                        ma = fmaxf(ma, fmaxf(fmaxf(e[0], e[1]), fmaxf(e[4], e[5])) + bias);
                        mb = fmaxf(mb, fmaxf(fmaxf(e[2], e[3]), fmaxf(e[6], e[7])) + bias);
                    }
                    ma = fmaxf(ma, __shfl_xor_sync(~0u, ma, 1)); mb = fmaxf(mb, __shfl_xor_sync(~0u, mb, 1));
                    ma = fmaxf(ma, __shfl_xor_sync(~0u, ma, 2)); mb = fmaxf(mb, __shfl_xor_sync(~0u, mb, 2));
                    na = -ma * CS; nb = -mb * CS;
                }
                PROFC(8 + 3 * hf);
                {
                    WAIT(B_VRFULL, 0);
                    float o[16] = {}, rs[4] = {};
                    uint32_t pk[2];
                    const uint32_t va = sb + OFF_Y + Y_VR + (kg0 + ((lane >> 3) & 1)) * 896 + (3 * w + (lane >> 4)) * 128 + (lane & 7) * 16;
#pragma unroll
                    for (int pp = 0; pp < 17; pp++) {
                        uint32_t B[8];
                        const uint32_t v = va + pp * 1792 + (pp == 16 || (pp >= 9 && kg0 + 2 * pp >= 32) ? Y_VOWN - 32 * 896 : 0);
                        ldsm4t(v, B); ldsm4t(v + 256, B + 4);
                        float e[8];
                        const float bias = __uint_as_float((pp < pmin ? 0xFF800000u : 0u) | ((pp < 2 ? B[0] : pk[pp & 1]) & p.zero));
#pragma unroll
                        for (int i = 0; i < 8; i++) e[i] = ex2(fmaf(s[8 * pp + i], CS, ((i & 2) ? nb : na) + bias));
                        const uint32_t p0 = pack2(e[0], e[1]), p1 = pack2(e[2], e[3]), p2 = pack2(e[4], e[5]), p3 = pack2(e[6], e[7]);
                        pk[pp & 1] = p3;
                        mma16816(rs, p0, p1, p2, p3, 0x3F803F80u, 0x3F803F80u);
#pragma unroll
                        for (int g = 0; g < 4; g++) mma16816(o + 4 * g, p0, p1, p2, p3, B[2 * g], B[2 * g + 1]);
                    }
                    PROFC(9 + 3 * hf);
                    const float ia = rcp(rs[0]), ib = rcp(rs[2]);
                    uint32_t* og = g_o + (size_t)(2 * r + hf) * 14336 + (7 * j + 3 * w) * 256 + wi * 64 + lane;
#pragma unroll
                    for (int g = 0; g < 4; g++) {
                        if ((g == 3 - 3 * w) ? ((q >> 1) == w) : true) {
                            og[g * 256] = pack2(o[4 * g] * ia, o[4 * g + 1] * ia);
                            og[g * 256 + 32] = pack2(o[4 * g + 2] * ib, o[4 * g + 3] * ib);
                        }
                    }
                    warp_arrive(BAR(B_PUB + 2 + hf));
                    PROFC(10 + 3 * hf);
                }
            }
        }
        uint32_t x1p[14];
        COORDS
        constexpr uint64_t DT = dconst(1024, 128, 0);
        const int tile = opaque((lds1(sb + M_EPOCH) & 1) * 34 + 2 * r + w);
        if (RUN(4)) {
            float ac[28];
            const uint32_t ad = mkdesc(sb + (w ? OFF_Y + HALF : OFF_X), DT), bd = mkdesc(sb + OFF_X + HALF, DB128) + kh;
            WAIT(B_WOFULL, 0);
            WAIT(B_MOD2, 0);
            WAIT(B_GFULL + w, 0);
            PROFC(28);
            reg_def<28>(ac);
#pragma unroll 1
            for (int u = 0; u < 4; u++) {
                if (u == 2) WAIT(B_XFULL + 2 + w, 1);
                WG_FENCE();
#pragma unroll
                for (int i = 0; i < 7; i++) wgmma_ss_56<DT, DB128>(ac, ad + (7 * u + i) * 128, bd + (7 * u + i) * 128, (u | i) != 0);
            }
            WG_COMMIT();
            WG_WAIT(0);
            reg_fence<28>(ac);
            PROFC(14);
            __syncwarp();
            if (lane < 3) mbar_arrive(BAR(B_EMPTY + 3 + lane));
            if (lane < 3 && w == 0) mbar_arrive(BAR(B_EMPTY + lane));
            float s1a = 0.f, s2a = 0.f, s1b = 0.f, s2b = 0.f;
            uint32_t* xo = g_x1 + (size_t)tile * 14336 + 7 * j * 256 + wi * 64 + lane;
#pragma unroll
            for (int g = 0; g < 7; g++) {
                const float2 ga = *(const float2*)(smem + M_G + (8 * g + 2 * q) * 4);
                x1p[2 * g] = pack2(fmaf(ga.x, ac[4 * g], bf_lo(xr[2 * g])), fmaf(ga.y, ac[4 * g + 1], bf_hi(xr[2 * g])));
                x1p[2 * g + 1] = pack2(fmaf(ga.x, ac[4 * g + 2], bf_lo(xr[2 * g + 1])), fmaf(ga.y, ac[4 * g + 3], bf_hi(xr[2 * g + 1])));
                st_relaxed(xo + g * 256, max(x1p[2 * g], 1u)); st_relaxed(xo + g * 256 + 32, max(x1p[2 * g + 1], 1u));
                const float u0 = bf_lo(x1p[2 * g]), u1 = bf_hi(x1p[2 * g]), u2 = bf_lo(x1p[2 * g + 1]), u3 = bf_hi(x1p[2 * g + 1]);
                s1a += u0 + u1; s2a += u0 * u0 + u1 * u1; s1b += u2 + u3; s2b += u2 * u2 + u3 * u3;
            }
            float ka = (q & 1) ? s2a : s1a, kb2 = (q & 1) ? s2b : s1b;
            ka += __shfl_xor_sync(~0u, (q & 1) ? s1a : s2a, 1); kb2 += __shfl_xor_sync(~0u, (q & 1) ? s1b : s2b, 1);
            const float kk = ((q & 2) ? kb2 : ka) + __shfl_xor_sync(~0u, (q & 2) ? ka : kb2, 2);
            st_relaxed((uint32_t*)g_st + ((tile * 8 + j) * 64 + 16 * wi + lr + 4 * (q & 2)) * 2 + (q & 1), max(__float_as_uint(kk), 1u));
            __syncwarp();
            if (lane < 2) mbar_arrive(BAR(B_PUB + 4 + w));
        } else reg_def<14>(x1p);
        PROFC(15);
        uint32_t h2a[32], h2b[24];
        if (RUN(3) || RUN(5) || RUN(6)) {
            const int fa = pass_f(fs, 0), fb = pass_f(fs, 1), fc = pass_f(fs, 2);
            uint32_t* h2g = g_h2 + (size_t)r * (224 * 512) + (8 * w + 2 * wi) * 32 + lane;
            const uint32_t a0 = mkdesc(sb + OFF_Y + w * HALF, DT);
            {
                WAIT(B_GFULL + 2 + w, 0);
                PROFC(16);
                float2 sa, sbb;
                {
                    uint2 u[16];
#pragma unroll
                    for (int i = 0; i < 16; i++) { const float2 v = lds2f(sb + OFF_X + X_STAT + w * 4096 + ((i >> 1) * 64 + 16 * wi + lr + 8 * (i & 1)) * 8); u[i] = make_uint2(__float_as_uint(v.x), __float_as_uint(v.y)); }
#pragma unroll 1
                    for (;;) {
                        uint32_t mn = ~0u;
#pragma unroll
                        for (int i = 0; i < 16; i++) mn = min(mn, min(u[i].x, u[i].y));
                        if (!__any_sync(~0u, mn == 0u) || sc) break;
#pragma unroll
                        for (int i = 0; i < 16; i++) u[i] = ld_relaxed2(g_st + (tile * 8 + (i >> 1)) * 64 + 16 * wi + lr + 8 * (i & 1));
                    }
                    sa = make_float2(0.f, 0.f); sbb = sa;
#pragma unroll
                    for (int i = 0; i < 16; i += 2) {
                        sa.x += __uint_as_float(u[i].x); sa.y += __uint_as_float(u[i].y);
                        sbb.x += __uint_as_float(u[i + 1].x); sbb.y += __uint_as_float(u[i + 1].y);
                    }
                }
                warp_arrive(BAR(B_EMPTY + 6));
                uint32_t ra2, na2, rb2, nb2;
                ln_coeffs(sa.x * (1.f / DM), sa.y * (1.f / DM), ra2, na2);
                ln_coeffs(sbb.x * (1.f / DM), sbb.y * (1.f / DM), rb2, nb2);
                const uint32_t ha = sb + OFF_Y + w * HALF + (lane >> 4) * 1024 + (2 * wi + ((lane >> 3) & 1)) * 128 + (lane & 7) * 16;
                const uint32_t sta = sb + M_ST + q * 16;
                const uint32_t* xg = g_x1 + (size_t)tile * 14336 + wi * 64 + lane;
                uint32_t x[8];
                uint4 st[2];
                auto load = [&](int s) {
                    if (s == 4) WAIT(B_XFULL + 4 + w, 1);
                    ldsm4(ha + s * 4096, x); ldsm4(ha + s * 4096 + 2048, x + 4);
                    st[0] = lds4(sta + s * 128); st[1] = lds4(sta + s * 128 + 64);
                };
                auto prep = [&](int s, uint32_t* f) {
                    while (__any_sync(~0u, min(min(min(x[0], x[1]), min(x[2], x[3])), min(min(x[4], x[5]), min(x[6], x[7]))) == 0u) && !sc) {
#pragma unroll
                        for (int i = 0; i < 8; i++) x[i] = ld_relaxed(xg + (4 * s + (i >> 1)) * 256 + (i & 1) * 32);
                    }
#pragma unroll
                    for (int i = 0; i < 2; i++) {
                        f[4 * i] = hfma2(hfma2(x[4 * i], ra2, na2), st[i].x, st[i].y); f[4 * i + 1] = hfma2(hfma2(x[4 * i + 1], rb2, nb2), st[i].x, st[i].y);
                        f[4 * i + 2] = hfma2(hfma2(x[4 * i + 2], ra2, na2), st[i].z, st[i].w); f[4 * i + 3] = hfma2(hfma2(x[4 * i + 3], rb2, nb2), st[i].z, st[i].w);
                    }
                    if (s < 13) load(s + 1);
                    stsm4(ha + s * 4096, f[0], f[1], f[2], f[3]); stsm4(ha + s * 4096 + 2048, f[4], f[5], f[6], f[7]);
                };
                float ac[128];
                uint32_t fr[3][8];
                const uint32_t bx = mkdesc(sb, DB128);
                reg_def<128>(ac);
                load(0);
                if (RUN(3)) prep(0, fr[0]);
                PROFC(17);
#pragma unroll
                for (int s = 0; s < 14; s++) {
                    if (RUN(s < 6 ? 3 : 5)) {
                        const uint32_t* f = fr[s % 3];
                        const uint32_t bd = bx + (slot_off(s % 7) >> 4);
                        WAIT(B_FULL + s % 7, s >= 7);
                        WG_FENCE();
                        wgmma_rs_256<DB128>(ac, f[0], f[1], f[2], f[3], bd, s != 0);
                        wgmma_rs_256<DB128>(ac, f[4], f[5], f[6], f[7], bd + 128, 1);
                        WG_COMMIT();
                        if (s < 13) prep(s + 1, fr[(s + 1) % 3]);
                        if (s > 0) { WG_WAIT(1); warp_arrive(BAR(B_EMPTY + (s - 1) % 7)); }
                    }
                }
                PROFC(18);
                fence_async_smem();
                WG_WAIT(0);
                reg_fence<128>(ac);
                warp_arrive(BAR(B_EMPTY + 6));
#pragma unroll
                for (int g = 0; g < 16; g++) {
                    h2a[2 * g] = hmul2(pack2_relu(ac[4 * g], ac[4 * g + 1]), pack2(ac[64 + 4 * g], ac[64 + 4 * g + 1]));
                    h2a[2 * g + 1] = hmul2(pack2_relu(ac[4 * g + 2], ac[4 * g + 3]), pack2(ac[64 + 4 * g + 2], ac[64 + 4 * g + 3]));
                    h2g[(fa / 8 + g) * 512] = h2a[2 * g]; h2g[(fa / 8 + g) * 512 + 32] = h2a[2 * g + 1];
                }
                warp_arrive(BAR(B_PUB + 6));
                bar_sync(1 + w, 128);
            }
            PROFC(19);
            {
                float ac[64];
                reg_def<64>(ac);
                const uint32_t bx = mkdesc(sb, dconst(8192, 1024, 1));
#pragma unroll kB
                for (int s = 0; s < 7; s++) {
                    WAIT(B_FULL + s, 0);
                    const uint32_t ad = a0 + s * 512, bd = bx + (slot_off(s) >> 4);
                    WG_FENCE();
#pragma unroll
                    for (int k = 0; k < 4; k++) wgmma_ss_128<DT, DB128>(ac, ad + k * 128, bd + k * 128, (s | k) != 0);
                    WG_COMMIT();
                    if (s > 0) { WG_WAIT(1); warp_arrive(BAR(B_EMPTY + s - 1)); }
                }
                WG_WAIT(0);
                reg_fence<64>(ac);
                warp_arrive(BAR(B_EMPTY + 6));
#pragma unroll
                for (int g = 0; g < 8; g++) {
                    h2b[2 * g] = hmul2(pack2_relu(ac[4 * g], ac[4 * g + 1]), pack2(ac[32 + 4 * g], ac[32 + 4 * g + 1]));
                    h2b[2 * g + 1] = hmul2(pack2_relu(ac[4 * g + 2], ac[4 * g + 3]), pack2(ac[32 + 4 * g + 2], ac[32 + 4 * g + 3]));
                    h2g[(fb / 8 + g) * 512] = h2b[2 * g]; h2g[(fb / 8 + g) * 512 + 32] = h2b[2 * g + 1];
                }
                warp_arrive(BAR(B_PUB + 7));
            }
            PROFC(27);
            {
                float ac[32];
                reg_def<32>(ac);
                const uint32_t bx = mkdesc(sb, dconst(4096, 512, 2));
#pragma unroll kC
                for (int s = 0; s < 7; s++) {
                    WAIT(B_FULL + s, 1);
                    const uint32_t ad = a0 + p.zero + s * 512, bd = bx + (slot_off(s) >> 4);
                    WG_FENCE();
#pragma unroll
                    for (int k = 0; k < 4; k++) wgmma_ss_64<DT, dconst(4096, 512, 2)>(ac, ad + k * 128, bd + k * 64, (s | k) != 0);
                    WG_COMMIT();
                    if (s > 0) { WG_WAIT(1); warp_arrive(BAR(B_EMPTY + s - 1)); }
                }
                WG_WAIT(0);
                reg_fence<32>(ac);
                __syncwarp();
                if (lane < 6) mbar_arrive(BAR(B_EMPTY + 6 + lane));
                PROFC(20);
#pragma unroll
                for (int g = 0; g < 4; g++) {
                    h2b[16 + 2 * g] = hmul2(pack2_relu(ac[4 * g], ac[4 * g + 1]), pack2(ac[16 + 4 * g], ac[16 + 4 * g + 1]));
                    h2b[16 + 2 * g + 1] = hmul2(pack2_relu(ac[4 * g + 2], ac[4 * g + 3]), pack2(ac[16 + 4 * g + 2], ac[16 + 4 * g + 3]));
                    h2g[(fc / 8 + g) * 512] = h2b[16 + 2 * g]; h2g[(fc / 8 + g) * 512 + 32] = h2b[16 + 2 * g + 1];
                }
                warp_arrive(BAR(B_PUB + 8));
                asm volatile("barrier.cluster.wait.aligned;" ::: "memory");
                if (lane == 0 && !sc) {
                    uint32_t rb;
                    asm volatile("mapa.shared::cluster.u32 %0, %1, %2;" : "=r"(rb) : "r"(BAR(B_PEER)), "r"(kh ^ 1));
                    asm volatile("mbarrier.arrive.relaxed.cluster.shared::cluster.b64 _, [%0];" ::"r"(rb) : "memory");
                }
            }
        } else { reg_def<32>(h2a); reg_def<24>(h2b); }
        PROFC(21);
        if (RUN(7)) {
            float ac[56];
            reg_def<56>(ac);
            constexpr uint64_t DAN = dconst(2048, 128, 0);
            constexpr uint64_t DW = dconst(128, 512, 0);
            const uint32_t bx = mkdesc(sb, DW);
#pragma unroll
            for (int e = 0; e < 4; e++) {
                WAIT(B_FULL + e, 0);
                const uint32_t bd = bx + (slot_off(e) >> 4);
                const uint32_t* hh = e < 2 ? h2a + 16 * e : h2b + 16 * (e - 2);
                WG_FENCE();
#pragma unroll
                for (int k = 0; k < (e < 3 ? 4 : 2); k++) wgmma_rs_112<DW>(ac, hh[4 * k], hh[4 * k + 1], hh[4 * k + 2], hh[4 * k + 3], bd + (k >> 1) * 512 + (k & 1) * 16, (e | k) != 0);
                WG_COMMIT();
                if (e > 0) { WG_WAIT(1); warp_arrive(BAR(B_EMPTY + e - 1)); }
            }
            PROFC(22);
            const uint32_t ax = mkdesc(sb + 8192 + w * 1024, DAN);
#pragma unroll kG2
            for (int e = 4; e < 25; e++) {
                WAIT(B_FULL + e % 12, e >= 12 && e < 24);
                if (e == 16) PROFC(23);
                const uint32_t z = (e / 12) * p.zero;
                const uint32_t ad = ax + z + (slot_off(e % 12) >> 4), bd = bx + z + (slot_off(e % 12) >> 4);
                WG_FENCE();
                wgmma_ss_112<DAN, DW>(ac, ad, bd, 1);
                wgmma_ss_112<DAN, DW>(ac, ad + 256, bd + 16, 1);
                WG_COMMIT();
                if (e < 14) { WG_WAIT(1); warp_arrive(BAR(B_EMPTY + (e - 1) % 12)); }
            }
            mbar_wait_cluster(BAR(B_PEER), sc);
            WG_WAIT(0);
            reg_fence<56>(ac);
            PROFC(24);
            uint32_t rdst, rbar;
            asm volatile("mapa.shared::cluster.u32 %0, %1, %2;" : "=r"(rdst) : "r"(sb + OFF_Y + (5 + w) * 16384 + t * 16), "r"(kh ^ 1 ^ sc));
            asm volatile("mapa.shared::cluster.u32 %0, %1, %2;" : "=r"(rbar) : "r"(BAR(B_XCH + w)), "r"(kh ^ 1 ^ sc));
#define ACG(g, i) ac[4 * (g) + (i)]
#pragma unroll
            for (int g = 0; g < 7; g++) {
                const float v0 = kh ? ACG(g, 0) : ACG(g + 7, 0), v1 = kh ? ACG(g, 1) : ACG(g + 7, 1);
                const float v2 = kh ? ACG(g, 2) : ACG(g + 7, 2), v3 = kh ? ACG(g, 3) : ACG(g + 7, 3);
                if (!sc) asm volatile("st.async.shared::cluster.mbarrier::complete_tx::bytes.v4.f32 [%0], {%1,%2,%3,%4}, [%5];"
                             ::"r"(rdst + g * 2048), "f"(v0), "f"(v1), "f"(v2), "f"(v3), "r"(rbar) : "memory");
            }
            mbar_wait_cluster(BAR(B_XCH + w), sc);
            PROFC(25);
            bf16* og = (sc ? (bf16*)(g_h2 + 16 * 224 * 512) : p.out + (size_t)128 * r * DM) + (size_t)ra * DM + 56 * j + 2 * q;
#pragma unroll
            for (int g = 0; g < 7; g++) {
                const uint4 rv = *(const uint4*)(smem + OFF_Y + (5 + w) * 16384 + t * 16 + g * 2048);
                const float2 gb = *(const float2*)(smem + M_G + 224 + (8 * g + 2 * q) * 4);
                const float v0 = (kh ? ACG(g + 7, 0) : ACG(g, 0)) + __uint_as_float(rv.x), v1 = (kh ? ACG(g + 7, 1) : ACG(g, 1)) + __uint_as_float(rv.y);
                const float v2 = (kh ? ACG(g + 7, 2) : ACG(g, 2)) + __uint_as_float(rv.z), v3 = (kh ? ACG(g + 7, 3) : ACG(g, 3)) + __uint_as_float(rv.w);
                *(uint32_t*)(og + 8 * g) = pack2(fmaf(gb.x, v0, bf_lo(x1p[2 * g])), fmaf(gb.y, v1, bf_hi(x1p[2 * g])));
                *(uint32_t*)(og + 8 * DM + 8 * g) = pack2(fmaf(gb.x, v2, bf_lo(x1p[2 * g + 1])), fmaf(gb.y, v3, bf_hi(x1p[2 * g + 1])));
            }
        }
        PROFC(26);
        bar_sync(1 + w, 128);
        if (wi == 0) warp_arrive(BAR(B_DONE));
    } else {
        const int lane = fresh_tid() & 31;
        const bool early = kh == 0, gemv = r < 14;
        const int mcol = early ? 16 * (4 * r + nq) : 2 * DM + 32 * (4 * r + nq);
        const uint32_t wmbuf = sb + OFF_Y + HALF;
        asm volatile("setmaxnreg.dec.sync.aligned.u32 56;");
        if (warp == 9) {
#pragma unroll
            for (int i = 56; i < 64; i++) init_e(BAR(i), 1);
            fence_async_smem();
        }
        if (warp == 8) { init_e(BAR(B_WMFULL), 2); fence_async_smem(); }
        bar_arrive(0, 384);
        asm volatile("barrier.cluster.arrive.relaxed.aligned;" ::: "memory");
        uint32_t target = 0;
        if (warp == 8) {
            if (!sc) {
                expect_e(BAR(B_WMFULL), gemv ? 28672 >> early : 0);
                if (early && gemv) { tma3_e(wmbuf, &p.wm, mcol, 0, 0, BAR(B_WMFULL)); tma3_e(wmbuf + 7168, &p.wm, mcol, 224, 0, BAR(B_WMFULL)); }
#pragma unroll 1
                for (int kb = 0; kb < 7; kb++) {
                    expect_e(BAR(B_XFULL + kb), 16384);
                    tma3_e(sb + OFF_X + kb * 16384, &p.xm, 64 * kb, 128 * r, 0, BAR(B_XFULL + kb));
                }
            }
#pragma unroll 1
            for (int mt = 0; mt < 4; mt++) {
                if (mt == 1) {
                    if (!early && gemv) {
#pragma unroll 1
                        for (int k = 0; k < 4; k++) tma3_e(wmbuf + k * 7168, &p.wm, mcol + (k >> 1) * 16, (k & 1) * 224, 0, BAR(B_WMFULL));
                    }
                    bar_sync(9, 384);
                    if (sc) return;
                    mbar_wait(BAR(B_MOD1), 0);
                    mbar_wait(BAR(B_WMFREE), 0);
                }
                if (mt == 2) mbar_wait(BAR(B_XFREE), 0);
                if (mt == 3) mbar_wait(BAR(B_VRFULL), 0);
                const uint32_t bar = BAR(mt == 3 ? B_WOFULL : B_FULLK + mt), dst = sb + (mt < 2 ? OFF_Y : OFF_X) + (mt & 1) * HALF;
                const int c0 = (mt < 2 ? DM + DM * mt : 0) + 56 * j - 8 * kh;
                if (!sc) {
                    expect_e(bar, HALF);
                    tma3_e(dst, mt == 3 ? &p.wo : &p.qkv, c0, 0, 0, bar);
                    tma3_e(dst + HALF / 2, mt == 3 ? &p.wo : &p.qkv, c0, 224, 0, bar);
                }
            }
            expect_e(BAR(B_XCH), 14336);
            expect_e(BAR(B_XCH + 1), 14336);
        } else {
            if (warp == 10 && !sc) {
                l2_prefetch_e((const char*)p.wqkv + (size_t)b * 9408, 9408);
                if (lane == 0) sts1(sb + M_EPOCH, atomicAdd(&g_ticket, 1u) / NCTA);
            }
            if (warp == 11) {
#pragma unroll
                for (int i = 0; i < 8; i++) {
                    const int wd = lane + 32 * i;
                    const uint32_t cb = i < 7 ? __ldg((const uint32_t*)p.c + wd) : 0u;
                    sts1(wmbuf + 28672 + (wd >> 3) * 32 + (wd & 3) * 8 + (wd & 4), pack2(silu_bf(cb & 0xFFFFu), silu_bf(cb >> 16)));
                }
            }
            bar_sync(9, 384);
            if (sc) return;
            target = lds1(sb + M_EPOCH) + 1;
            const uint32_t tag = target & 0xFFFFu;
            if (warp == 11) {
                warp_arrive(BAR(B_WMFULL));
                mbar_wait(BAR(B_GEMV), 0);
                float sum = 0.f;
#pragma unroll
                for (int i = 0; i < 8; i++) sum += *(const float*)(smem + OFF_Y + HALF + 29696 + (i * 32 + (early ? lane & 15 : lane)) * 4);
                const uint32_t word = (pack2(sum, 0.f) << 16) | tag;
                if (gemv) {
                    uint32_t* mg = g_mod + mcol + (early ? (lane & 15) + (lane >> 4) * 4 * 6 * DM : lane);
#pragma unroll
                    for (int i = 0; i < 8; i++) if (i < 4 || !early) st_relaxed(mg + i * 6 * DM, word);
                }
                warp_arrive(BAR(B_WMFREE));
            }
            const uint4* modp = (const uint4*)g_mod + (r & 7) * (6 * DM / 4);
            const bool p2 = warp == 11;
            mbar_wait(BAR(p2 ? B_PUB : B_XFULL + 4), 0);
#pragma unroll 1
            for (int it = p2 ? 0 : warp - 9; it < (p2 ? 2 : warp - 8); it++) {
                const int i0 = lane + 32 * it, imax = p2 ? 251 : 223;
                uint4 v[4];
#pragma unroll 1
                for (int n = 0;; n++) {
                    uint32_t bad = 0;
#pragma unroll
                    for (int k = 0; k < 4; k++) {
                        const int i = min(i0 + 64 * k, imax);
                        v[k] = ld_relaxed4(modp + (i < 224 ? (p2 ? 336 : 0) + i : (i < 238 ? 14 * j + i : 14 * j + i + 322)));
                        bad |= (v[k].x ^ tag) | (v[k].y ^ tag) | (v[k].z ^ tag) | (v[k].w ^ tag);
                    }
                    if (!__any_sync(~0u, bad & 0xFFFFu)) break;
                    if (n > SPIN_LIMIT) __trap();
                }
#pragma unroll
                for (int k = 0; k < 4; k++) {
                    const int i = min(i0 + 64 * k, imax);
                    if (i < 224) {
                        const int isc = i >= 112, c4 = i - 112 * isc;
                        const float one = isc ? 1.f : 0.f;
                        const uint32_t a = sb + M_ST + (c4 >> 2) * 64 + (c4 & 1) * 32 + (c4 & 2) * 4 + (isc ? 0 : 4);
                        sts1(a, pack2(bf_hi(v[k].x) + one, bf_hi(v[k].y) + one));
                        sts1(a + 16, pack2(bf_hi(v[k].z) + one, bf_hi(v[k].w) + one));
                    } else {
                        sts4(sb + M_G + (i - 224) * 16, make_uint4(v[k].x & 0xFFFF0000u, v[k].y & 0xFFFF0000u, v[k].z & 0xFFFF0000u, v[k].w & 0xFFFF0000u));
                    }
                }
                warp_arrive(BAR(p2 ? B_MOD2 : B_MOD1));
            }
            if (warp == 9) {
#pragma unroll 1
                for (int kv = 0; kv < 2; kv++) {
                    mbar_wait(BAR(B_PUB + kv), 0);
                    wait_flags(g_flag + b * 128 + lane, target, (r >= 2 ? 6u : r == 1 ? 2u : 0u) << (8 * kv));
                    fence_async_global();
                    const uint32_t dst = sb + OFF_Y + (kv ? Y_VR : Y_K);
                    expect_e(BAR(B_KRFULL + kv), r >= 2 ? 28672 : r == 1 ? 14336 : 0);
                    if (r >= 2) bulk_e(dst, g_kv + (size_t)((b - 16) * 2 + kv) * 3584, 14336, BAR(B_KRFULL + kv));
                    if (r >= 1) bulk_e(dst + 14336, g_kv + (size_t)((b - 8) * 2 + kv) * 3584, 14336, BAR(B_KRFULL + kv));
                }
            } else if (warp == 11) {
                mbar_wait(BAR(B_VRFULL), 0);
                l2_prefetch_e((const char*)p.wg + (size_t)b * 12544, 12544);
                l2_prefetch_e((const char*)p.wu + (size_t)b * 12544, 12544);
#pragma unroll 1
                for (int k = 0; k < (r < 12 ? 2 : 1); k++) {
                    const int u = 28 * kh + r + 16 * k;
                    expect_e(BAR(B_XFULL + k), 7168);
                    tma3_e(sb + OFF_Y + 102400, &p.dn, 0, 32 * u, 14 * nq, BAR(B_XFULL + k));
                    mbar_wait(BAR(B_XFULL + k), 1);
                    asm volatile("{\n.reg .pred p;\nelect.sync _|p, 0xffffffff;\n@p cp.async.bulk.global.shared::cta.bulk_group [%0], [%1], 7168;\n"
                                 "cp.async.bulk.commit_group;\ncp.async.bulk.wait_group 0;\n}" ::"l"(g_wd + (size_t)(u * 4 + nq) * 1792), "r"(sb + OFF_Y + 102400) : "memory");
                    __syncwarp();
                }
                warp_arrive(BAR(B_WMFREE));
                fence_gpu();
                if (lane < 16) st_relaxed(g_flag + (8 * lane + j) * 128 + 96 + r, target);
            }
        }
        if (warp == 8 || warp == 11) {
            const int sec = warp == 11;
            if (sec) ring_loader<1>(p, sb, r, j, lane); else ring_loader<0>(p, sb, r, j, lane);
            mbar_wait(BAR(B_DONE), 0);
        } else if (warp == 9) {
#pragma unroll
            for (int ev = 0; ev < 4; ev++) { expect_e(BAR(B_GFULL + ev), ev < 2 ? HALF / 2 : 16384 + 4096); expect_e(BAR(B_XFULL + 2 + ev), ev < 2 ? HALF / 2 : HALF - 16384); }
            mbar_wait(BAR(B_PUB + 2), 0);
            const uint32_t* fp = g_flag + b * 128 + 32 + lane;
            const int par = (target - 1) & 1;
#pragma unroll 1
            for (int n = 0, ev = 0; ev < 4; n++) {
                if (ev == 1) { mbar_wait(BAR(B_WMFREE), 1); mbar_wait(BAR(B_PUB + 3), 0); }
                uint32_t ok = __ballot_sync(~0u, (int)(ld_relaxed(fp) - target) >= 0) >> (8 * ev);
                while ((ok & 0xFFu) == 0xFFu) {
                    asm volatile("fence.acquire.gpu;" ::: "memory");
                    fence_async_global();
                    const int tile = 2 * r + (ev & 1) + (ev >> 1) * par * 34;
                    const uint32_t dst = sb + (ev == 0 ? OFF_X : OFF_Y + (ev & 1) * HALF), first = ev < 2 ? HALF / 2 : 16384;
                    const char* src = (const char*)(g_ox + (size_t)((ev >> 1) * 34 + tile) * 14336);
                    if (ev >= 2) bulk_e(sb + OFF_X + X_STAT + (ev & 1) * 4096, g_st + tile * 512, 4096, BAR(B_GFULL + ev));
                    bulk_e(dst, src, first, BAR(B_GFULL + ev));
                    bulk_e(dst + first, src + first, HALF - first, BAR(B_XFULL + 2 + ev));
                    if (ev) PROFH(4 + ev);
                    ev++; ok >>= 8;
                }
                if (n > SPIN_LIMIT) __trap();
            }
            mbar_wait(BAR(B_XFULL + 5), 1);
#pragma unroll 1
            for (int hf = 0; hf < 2; hf++) {
                const int tile = (par ^ 1) * 34 + 2 * r + hf;
                uint4* xz = (uint4*)(g_x1 + (size_t)tile * 14336 + j * 1792) + lane;
#pragma unroll
                for (int i = 0; i < 14; i++) xz[i * 32] = make_uint4(0, 0, 0, 0);
                ((uint4*)(g_st + (tile * 8 + j) * 64))[lane] = make_uint4(0, 0, 0, 0);
            }
#pragma unroll 1
            for (int ps = 0; ps < 3; ps++) {
                mbar_wait(BAR(B_PUB + 6 + ps), 0);
                wait_flags(g_flag + b * 128 + 64 + lane, target, (0x55u << kh) << (8 * ps));
                warp_arrive(BAR(B_HRDY + ps));
                PROFH(9 + ps);
            }
        } else {
#pragma unroll 1
            for (int k = 0; k < 9; k++) {
                uint32_t* fp = k < 2 ? g_flag + (b + 8 * lane) * 128 + k * 8 + lane : g_flag + (8 * r + lane) * 128 + 16 + k * 8 + j;
                mbar_wait(BAR(B_PUB + k), 0);
                if (k != 4 && k != 5) fence_gpu();
                if (k < 2 ? (lane == 1 || lane == 2) : lane < 8) st_relaxed(fp, target);
                if (k >= 3 && k <= 5) PROFH(k - 3);
            }
        }
    }
}

typedef CUresult (*EncodeFn)(CUtensorMap*, CUtensorMapDataType, cuuint32_t, void*, const cuuint64_t*, const cuuint64_t*, const cuuint32_t*,
                             const cuuint32_t*, CUtensorMapInterleave, CUtensorMapSwizzle, CUtensorMapL2promotion, CUtensorMapFloatOOBfill);

static void make_map(EncodeFn fn, CUtensorMap* m, const void* ptr, uint64_t d0, uint64_t d1, uint64_t d2, uint64_t s1, uint64_t s2,
                     uint32_t b0, uint32_t b1, uint32_t b2, CUtensorMapSwizzle sw) {
    cuuint64_t dims[3] = {d0, d1, d2}, strides[2] = {s1, s2};
    cuuint32_t box[3] = {b0, b1, b2}, es[3] = {1, 1, 1};
    CUresult rc = fn(m, CU_TENSOR_MAP_DATA_TYPE_BFLOAT16, 3, (void*)ptr, dims, strides, box, es, CU_TENSOR_MAP_INTERLEAVE_NONE, sw,
                     CU_TENSOR_MAP_L2_PROMOTION_L2_128B, CU_TENSOR_MAP_FLOAT_OOB_FILL_NONE);
    (void)rc;
}

extern "C" void kernel_launch(void* const* d_in, const int* in_sizes, int n_in, void* d_out, int out_size) {
    (void)in_sizes; (void)n_in; (void)out_size;
    static EncodeFn fn = nullptr;
    if (!fn) {
        cudaDriverEntryPointQueryResult st;
        cudaGetDriverEntryPoint("cuTensorMapEncodeTiled", (void**)&fn, cudaEnableDefault, &st);
        cudaFuncSetAttribute(fused_block_kernel, cudaFuncAttributeMaxDynamicSharedMemorySize, SMEM_BYTES);
    }
    Params p;
    p.x = (const bf16*)d_in[0];
    const bf16* wqkv = (const bf16*)d_in[1];
    p.wqkv = wqkv;
    p.wop = (const bf16*)d_in[2];
    p.wg = (const bf16*)d_in[4];
    p.wu = (const bf16*)d_in[5];
    p.wd = (const bf16*)d_in[6];
    p.c = (const bf16*)d_in[7];
    p.wmod = (const bf16*)d_in[8];
    p.out = (bf16*)d_out;
    p.zero = 0;
    make_map(fn, &p.wm, p.wmod, 2688, 448, 1, 5376, 5376 * 448, 16, 224, 1, CU_TENSOR_MAP_SWIZZLE_NONE);
    make_map(fn, &p.xm, p.x, 448, 2048, 1, 896, 896 * 2048, 64, 128, 1, CU_TENSOR_MAP_SWIZZLE_128B);
    make_map(fn, &p.qkv, wqkv, 1344, 448, 1, 2688, 2688 * 448, 64, 224, 1, CU_TENSOR_MAP_SWIZZLE_128B);
    make_map(fn, &p.wo, p.wop, 448, 448, 1, 896, 896 * 448, 64, 224, 1, CU_TENSOR_MAP_SWIZZLE_128B);
    make_map(fn, &p.ga, p.wg, 64, 448, 28, 3584, 128, 64, 32, 2, CU_TENSOR_MAP_SWIZZLE_128B);
    make_map(fn, &p.ua, p.wu, 64, 448, 28, 3584, 128, 64, 32, 2, CU_TENSOR_MAP_SWIZZLE_128B);
    make_map(fn, &p.gb, p.wg, 64, 448, 28, 3584, 128, 64, 64, 1, CU_TENSOR_MAP_SWIZZLE_128B);
    make_map(fn, &p.ub, p.wu, 64, 448, 28, 3584, 128, 64, 64, 1, CU_TENSOR_MAP_SWIZZLE_128B);
    make_map(fn, &p.gc, p.wg, 32, 448, 56, 3584, 64, 32, 64, 1, CU_TENSOR_MAP_SWIZZLE_64B);
    make_map(fn, &p.uc, p.wu, 32, 448, 56, 3584, 64, 32, 64, 1, CU_TENSOR_MAP_SWIZZLE_64B);
    make_map(fn, &p.dn, p.wd, 8, 1792, 56, 896, 16, 8, 32, 14, CU_TENSOR_MAP_SWIZZLE_NONE);
    fused_block_kernel<<<GRID, 384, SMEM_BYTES>>>(p);
}
```

```cpp
#include <cuda_runtime.h>
#include <cuda_bf16.h>
#include <cuda.h>
#include <stdint.h>

typedef __nv_bfloat16 bf16;

template<uint64_t CB> __device__ __forceinline__ void wgmma_rs_56(float* d, uint32_t a0, uint32_t a1, uint32_t a2, uint32_t a3, uint32_t db, int sd) {
  asm volatile("{\n.reg .pred p;\n.reg .b64 b;\nsetp.ne.b32 p, %33, 0;\nmov.b64 b, {%32, %34};\n"
    "wgmma.mma_async.sync.aligned.m64n56k16.f32.bf16.bf16 {%0,%1,%2,%3,%4,%5,%6,%7,%8,%9,%10,%11,%12,%13,%14,%15,%16,%17,%18,%19,%20,%21,%22,%23,%24,%25,%26,%27}, {%28,%29,%30,%31}, b, p, 1, 1, 1;\n}\n"
    : "+f"(d[0]),"+f"(d[1]),"+f"(d[2]),"+f"(d[3]),"+f"(d[4]),"+f"(d[5]),"+f"(d[6]),"+f"(d[7]),"+f"(d[8]),"+f"(d[9]),"+f"(d[10]),"+f"(d[11]),"+f"(d[12]),"+f"(d[13]),"+f"(d[14]),"+f"(d[15]),"+f"(d[16]),"+f"(d[17]),"+f"(d[18]),"+f"(d[19]),"+f"(d[20]),"+f"(d[21]),"+f"(d[22]),"+f"(d[23]),"+f"(d[24]),"+f"(d[25]),"+f"(d[26]),"+f"(d[27])
    : "r"(a0), "r"(a1), "r"(a2), "r"(a3), "r"(db), "r"(sd), "n"((uint32_t)(CB >> 32)));
}
template<uint64_t CA, uint64_t CB> __device__ __forceinline__ void wgmma_ss_56(float* d, uint32_t da, uint32_t db, int sd) {
  asm volatile("{\n.reg .pred p;\n.reg .b64 a, b;\nsetp.ne.b32 p, %30, 0;\nmov.b64 a, {%28, %31};\nmov.b64 b, {%29, %32};\n"
    "wgmma.mma_async.sync.aligned.m64n56k16.f32.bf16.bf16 {%0,%1,%2,%3,%4,%5,%6,%7,%8,%9,%10,%11,%12,%13,%14,%15,%16,%17,%18,%19,%20,%21,%22,%23,%24,%25,%26,%27}, a, b, p, 1, 1, 0, 1;\n}\n"
    : "+f"(d[0]),"+f"(d[1]),"+f"(d[2]),"+f"(d[3]),"+f"(d[4]),"+f"(d[5]),"+f"(d[6]),"+f"(d[7]),"+f"(d[8]),"+f"(d[9]),"+f"(d[10]),"+f"(d[11]),"+f"(d[12]),"+f"(d[13]),"+f"(d[14]),"+f"(d[15]),"+f"(d[16]),"+f"(d[17]),"+f"(d[18]),"+f"(d[19]),"+f"(d[20]),"+f"(d[21]),"+f"(d[22]),"+f"(d[23]),"+f"(d[24]),"+f"(d[25]),"+f"(d[26]),"+f"(d[27])
    : "r"(da), "r"(db), "r"(sd), "n"((uint32_t)(CA >> 32)), "n"((uint32_t)(CB >> 32)));
}
template<uint64_t CB> __device__ __forceinline__ void wgmma_rs_256(float* d, uint32_t a0, uint32_t a1, uint32_t a2, uint32_t a3, uint32_t db, int sd) {
  asm volatile("{\n.reg .pred p;\n.reg .b64 b;\nsetp.ne.b32 p, %133, 0;\nmov.b64 b, {%132, %134};\n"
    "wgmma.mma_async.sync.aligned.m64n256k16.f32.bf16.bf16 {%0,%1,%2,%3,%4,%5,%6,%7,%8,%9,%10,%11,%12,%13,%14,%15,%16,%17,%18,%19,%20,%21,%22,%23,%24,%25,%26,%27,%28,%29,%30,%31,%32,%33,%34,%35,%36,%37,%38,%39,%40,%41,%42,%43,%44,%45,%46,%47,%48,%49,%50,%51,%52,%53,%54,%55,%56,%57,%58,%59,%60,%61,%62,%63,%64,%65,%66,%67,%68,%69,%70,%71,%72,%73,%74,%75,%76,%77,%78,%79,%80,%81,%82,%83,%84,%85,%86,%87,%88,%89,%90,%91,%92,%93,%94,%95,%96,%97,%98,%99,%100,%101,%102,%103,%104,%105,%106,%107,%108,%109,%110,%111,%112,%113,%114,%115,%116,%117,%118,%119,%120,%121,%122,%123,%124,%125,%126,%127}, {%128,%129,%130,%131}, b, p, 1, 1, 1;\n}\n"
    : "+f"(d[0]),"+f"(d[1]),"+f"(d[2]),"+f"(d[3]),"+f"(d[4]),"+f"(d[5]),"+f"(d[6]),"+f"(d[7]),"+f"(d[8]),"+f"(d[9]),"+f"(d[10]),"+f"(d[11]),"+f"(d[12]),"+f"(d[13]),"+f"(d[14]),"+f"(d[15]),"+f"(d[16]),"+f"(d[17]),"+f"(d[18]),"+f"(d[19]),"+f"(d[20]),"+f"(d[21]),"+f"(d[22]),"+f"(d[23]),"+f"(d[24]),"+f"(d[25]),"+f"(d[26]),"+f"(d[27]),"+f"(d[28]),"+f"(d[29]),"+f"(d[30]),"+f"(d[31]),"+f"(d[32]),"+f"(d[33]),"+f"(d[34]),"+f"(d[35]),"+f"(d[36]),"+f"(d[37]),"+f"(d[38]),"+f"(d[39]),"+f"(d[40]),"+f"(d[41]),"+f"(d[42]),"+f"(d[43]),"+f"(d[44]),"+f"(d[45]),"+f"(d[46]),"+f"(d[47]),"+f"(d[48]),"+f"(d[49]),"+f"(d[50]),"+f"(d[51]),"+f"(d[52]),"+f"(d[53]),"+f"(d[54]),"+f"(d[55]),"+f"(d[56]),"+f"(d[57]),"+f"(d[58]),"+f"(d[59]),"+f"(d[60]),"+f"(d[61]),"+f"(d[62]),"+f"(d[63]),"+f"(d[64]),"+f"(d[65]),"+f"(d[66]),"+f"(d[67]),"+f"(d[68]),"+f"(d[69]),"+f"(d[70]),"+f"(d[71]),"+f"(d[72]),"+f"(d[73]),"+f"(d[74]),"+f"(d[75]),"+f"(d[76]),"+f"(d[77]),"+f"(d[78]),"+f"(d[79]),"+f"(d[80]),"+f"(d[81]),"+f"(d[82]),"+f"(d[83]),"+f"(d[84]),"+f"(d[85]),"+f"(d[86]),"+f"(d[87]),"+f"(d[88]),"+f"(d[89]),"+f"(d[90]),"+f"(d[91]),"+f"(d[92]),"+f"(d[93]),"+f"(d[94]),"+f"(d[95]),"+f"(d[96]),"+f"(d[97]),"+f"(d[98]),"+f"(d[99]),"+f"(d[100]),"+f"(d[101]),"+f"(d[102]),"+f"(d[103]),"+f"(d[104]),"+f"(d[105]),"+f"(d[106]),"+f"(d[107]),"+f"(d[108]),"+f"(d[109]),"+f"(d[110]),"+f"(d[111]),"+f"(d[112]),"+f"(d[113]),"+f"(d[114]),"+f"(d[115]),"+f"(d[116]),"+f"(d[117]),"+f"(d[118]),"+f"(d[119]),"+f"(d[120]),"+f"(d[121]),"+f"(d[122]),"+f"(d[123]),"+f"(d[124]),"+f"(d[125]),"+f"(d[126]),"+f"(d[127])
    : "r"(a0), "r"(a1), "r"(a2), "r"(a3), "r"(db), "r"(sd), "n"((uint32_t)(CB >> 32)));
}
template<uint64_t CA, uint64_t CB> __device__ __forceinline__ void wgmma_ss_128(float* d, uint32_t da, uint32_t db, int sd) {
  asm volatile("{\n.reg .pred p;\n.reg .b64 a, b;\nsetp.ne.b32 p, %66, 0;\nmov.b64 a, {%64, %67};\nmov.b64 b, {%65, %68};\n"
    "wgmma.mma_async.sync.aligned.m64n128k16.f32.bf16.bf16 {%0,%1,%2,%3,%4,%5,%6,%7,%8,%9,%10,%11,%12,%13,%14,%15,%16,%17,%18,%19,%20,%21,%22,%23,%24,%25,%26,%27,%28,%29,%30,%31,%32,%33,%34,%35,%36,%37,%38,%39,%40,%41,%42,%43,%44,%45,%46,%47,%48,%49,%50,%51,%52,%53,%54,%55,%56,%57,%58,%59,%60,%61,%62,%63}, a, b, p, 1, 1, 0, 1;\n}\n"
    : "+f"(d[0]),"+f"(d[1]),"+f"(d[2]),"+f"(d[3]),"+f"(d[4]),"+f"(d[5]),"+f"(d[6]),"+f"(d[7]),"+f"(d[8]),"+f"(d[9]),"+f"(d[10]),"+f"(d[11]),"+f"(d[12]),"+f"(d[13]),"+f"(d[14]),"+f"(d[15]),"+f"(d[16]),"+f"(d[17]),"+f"(d[18]),"+f"(d[19]),"+f"(d[20]),"+f"(d[21]),"+f"(d[22]),"+f"(d[23]),"+f"(d[24]),"+f"(d[25]),"+f"(d[26]),"+f"(d[27]),"+f"(d[28]),"+f"(d[29]),"+f"(d[30]),"+f"(d[31]),"+f"(d[32]),"+f"(d[33]),"+f"(d[34]),"+f"(d[35]),"+f"(d[36]),"+f"(d[37]),"+f"(d[38]),"+f"(d[39]),"+f"(d[40]),"+f"(d[41]),"+f"(d[42]),"+f"(d[43]),"+f"(d[44]),"+f"(d[45]),"+f"(d[46]),"+f"(d[47]),"+f"(d[48]),"+f"(d[49]),"+f"(d[50]),"+f"(d[51]),"+f"(d[52]),"+f"(d[53]),"+f"(d[54]),"+f"(d[55]),"+f"(d[56]),"+f"(d[57]),"+f"(d[58]),"+f"(d[59]),"+f"(d[60]),"+f"(d[61]),"+f"(d[62]),"+f"(d[63])
    : "r"(da), "r"(db), "r"(sd), "n"((uint32_t)(CA >> 32)), "n"((uint32_t)(CB >> 32)));
}
template<uint64_t CA, uint64_t CB> __device__ __forceinline__ void wgmma_ss_64(float* d, uint32_t da, uint32_t db, int sd) {
  asm volatile("{\n.reg .pred p;\n.reg .b64 a, b;\nsetp.ne.b32 p, %34, 0;\nmov.b64 a, {%32, %35};\nmov.b64 b, {%33, %36};\n"
    "wgmma.mma_async.sync.aligned.m64n64k16.f32.bf16.bf16 {%0,%1,%2,%3,%4,%5,%6,%7,%8,%9,%10,%11,%12,%13,%14,%15,%16,%17,%18,%19,%20,%21,%22,%23,%24,%25,%26,%27,%28,%29,%30,%31}, a, b, p, 1, 1, 0, 1;\n}\n"
    : "+f"(d[0]),"+f"(d[1]),"+f"(d[2]),"+f"(d[3]),"+f"(d[4]),"+f"(d[5]),"+f"(d[6]),"+f"(d[7]),"+f"(d[8]),"+f"(d[9]),"+f"(d[10]),"+f"(d[11]),"+f"(d[12]),"+f"(d[13]),"+f"(d[14]),"+f"(d[15]),"+f"(d[16]),"+f"(d[17]),"+f"(d[18]),"+f"(d[19]),"+f"(d[20]),"+f"(d[21]),"+f"(d[22]),"+f"(d[23]),"+f"(d[24]),"+f"(d[25]),"+f"(d[26]),"+f"(d[27]),"+f"(d[28]),"+f"(d[29]),"+f"(d[30]),"+f"(d[31])
    : "r"(da), "r"(db), "r"(sd), "n"((uint32_t)(CA >> 32)), "n"((uint32_t)(CB >> 32)));
}
template<uint64_t CA, uint64_t CB> __device__ __forceinline__ void wgmma_ss_112(float* d, uint32_t da, uint32_t db, int sd) {
  asm volatile("{\n.reg .pred p;\n.reg .b64 a, b;\nsetp.ne.b32 p, %58, 0;\nmov.b64 a, {%56, %59};\nmov.b64 b, {%57, %60};\n"
    "wgmma.mma_async.sync.aligned.m64n112k16.f32.bf16.bf16 {%0,%1,%2,%3,%4,%5,%6,%7,%8,%9,%10,%11,%12,%13,%14,%15,%16,%17,%18,%19,%20,%21,%22,%23,%24,%25,%26,%27,%28,%29,%30,%31,%32,%33,%34,%35,%36,%37,%38,%39,%40,%41,%42,%43,%44,%45,%46,%47,%48,%49,%50,%51,%52,%53,%54,%55}, a, b, p, 1, 1, 0, 1;\n}\n"
    : "+f"(d[0]),"+f"(d[1]),"+f"(d[2]),"+f"(d[3]),"+f"(d[4]),"+f"(d[5]),"+f"(d[6]),"+f"(d[7]),"+f"(d[8]),"+f"(d[9]),"+f"(d[10]),"+f"(d[11]),"+f"(d[12]),"+f"(d[13]),"+f"(d[14]),"+f"(d[15]),"+f"(d[16]),"+f"(d[17]),"+f"(d[18]),"+f"(d[19]),"+f"(d[20]),"+f"(d[21]),"+f"(d[22]),"+f"(d[23]),"+f"(d[24]),"+f"(d[25]),"+f"(d[26]),"+f"(d[27]),"+f"(d[28]),"+f"(d[29]),"+f"(d[30]),"+f"(d[31]),"+f"(d[32]),"+f"(d[33]),"+f"(d[34]),"+f"(d[35]),"+f"(d[36]),"+f"(d[37]),"+f"(d[38]),"+f"(d[39]),"+f"(d[40]),"+f"(d[41]),"+f"(d[42]),"+f"(d[43]),"+f"(d[44]),"+f"(d[45]),"+f"(d[46]),"+f"(d[47]),"+f"(d[48]),"+f"(d[49]),"+f"(d[50]),"+f"(d[51]),"+f"(d[52]),"+f"(d[53]),"+f"(d[54]),"+f"(d[55])
    : "r"(da), "r"(db), "r"(sd), "n"((uint32_t)(CA >> 32)), "n"((uint32_t)(CB >> 32)));
}
template<uint64_t CB> __device__ __forceinline__ void wgmma_rs_112(float* d, uint32_t a0, uint32_t a1, uint32_t a2, uint32_t a3, uint32_t db, int sd) {
  asm volatile("{\n.reg .pred p;\n.reg .b64 b;\nsetp.ne.b32 p, %61, 0;\nmov.b64 b, {%60, %62};\n"
    "wgmma.mma_async.sync.aligned.m64n112k16.f32.bf16.bf16 {%0,%1,%2,%3,%4,%5,%6,%7,%8,%9,%10,%11,%12,%13,%14,%15,%16,%17,%18,%19,%20,%21,%22,%23,%24,%25,%26,%27,%28,%29,%30,%31,%32,%33,%34,%35,%36,%37,%38,%39,%40,%41,%42,%43,%44,%45,%46,%47,%48,%49,%50,%51,%52,%53,%54,%55}, {%56,%57,%58,%59}, b, p, 1, 1, 1;\n}\n"
    : "+f"(d[0]),"+f"(d[1]),"+f"(d[2]),"+f"(d[3]),"+f"(d[4]),"+f"(d[5]),"+f"(d[6]),"+f"(d[7]),"+f"(d[8]),"+f"(d[9]),"+f"(d[10]),"+f"(d[11]),"+f"(d[12]),"+f"(d[13]),"+f"(d[14]),"+f"(d[15]),"+f"(d[16]),"+f"(d[17]),"+f"(d[18]),"+f"(d[19]),"+f"(d[20]),"+f"(d[21]),"+f"(d[22]),"+f"(d[23]),"+f"(d[24]),"+f"(d[25]),"+f"(d[26]),"+f"(d[27]),"+f"(d[28]),"+f"(d[29]),"+f"(d[30]),"+f"(d[31]),"+f"(d[32]),"+f"(d[33]),"+f"(d[34]),"+f"(d[35]),"+f"(d[36]),"+f"(d[37]),"+f"(d[38]),"+f"(d[39]),"+f"(d[40]),"+f"(d[41]),"+f"(d[42]),"+f"(d[43]),"+f"(d[44]),"+f"(d[45]),"+f"(d[46]),"+f"(d[47]),"+f"(d[48]),"+f"(d[49]),"+f"(d[50]),"+f"(d[51]),"+f"(d[52]),"+f"(d[53]),"+f"(d[54]),"+f"(d[55])
    : "r"(a0), "r"(a1), "r"(a2), "r"(a3), "r"(db), "r"(sd), "n"((uint32_t)(CB >> 32)));
}

constexpr int DM = 448;
constexpr int NCTA = 128;
#define MAPPING 1
#define GRID 132
#define PINGPONG 0
#define WIN 6
#define WIN_END 25
#define UNR_G2 21
#define UNR_B 7
#define UNR_C 7
constexpr int kG2 = UNR_G2, kB = UNR_B, kC = UNR_C;
#define PACE 1
#define PACE_END 6
#define MAP_S 4
constexpr int SPIN_LIMIT = 1 << 22;

constexpr uint32_t OFF_X = 0, OFF_Y = 114688, OFF_MISC = 229376, SMEM_BYTES = 232448;
constexpr uint32_t Y_VR = 0, Y_K = 28672, Y_KOWN = 57344, Y_VOWN = 71680, Y_Q = 86016;
constexpr uint32_t HALF = 57344;
constexpr uint32_t M_BAR = OFF_MISC;
constexpr uint32_t M_ST = OFF_MISC + 512;
constexpr uint32_t M_G = OFF_MISC + 2304;
constexpr uint32_t M_EPOCH = OFF_MISC + 3040;
enum { B_XFULL = 0, B_FULLK = 7, B_FULLV = 8, B_FULLQ, B_KRFULL, B_VRFULL, B_WOFULL, B_XCH, B_FULL = 16, B_MOD1 = 28, B_MOD2, B_WMFULL,
       B_EMPTY = 32, B_XFREE = B_EMPTY + 12, B_GEMV, B_PEER,
       B_PUB = 47,
       B_WMFREE = 56, B_HRDY, B_GFULL = B_HRDY + 3, B_DONE = 31 };
constexpr uint32_t X_STAT = 49152;

__device__ uint32_t g_ticket;
__device__ __align__(128) uint32_t g_mod[8 * 6 * DM];
__device__ __align__(128) uint32_t g_flag[144 * 128];
__device__ __align__(128) uint32_t g_kv[17 * 8 * 2 * 3584];
__device__ __align__(128) uint32_t g_ox[3 * 34 * 14336];
#define g_o g_ox
#define g_x1 (g_ox + 34 * 14336)
__device__ __align__(128) float2 g_st[2 * 34 * 8 * 64];
__device__ __align__(128) uint32_t g_wd[56 * 4 * 1792];
__device__ __align__(128) uint32_t g_h2[17 * 224 * 512];
#define PROFH(id)
#define PROFH1(id)
#define PROFC(id)

struct alignas(64) Params {
    CUtensorMap wm, xm, qkv, wo, ga, ua, gb, ub, gc, uc, dn;
    const bf16 *x, *c, *wqkv, *wmod, *wg, *wu, *wd, *wop;
    bf16* out;
    uint32_t zero;
};

__device__ __forceinline__ void mbar_init(uint32_t bar, int cnt) { asm volatile("mbarrier.init.shared::cta.b64 [%0], %1;" ::"r"(bar), "r"(cnt) : "memory"); }
__device__ __forceinline__ void mbar_expect_tx(uint32_t bar, uint32_t bytes) { asm volatile("mbarrier.arrive.expect_tx.shared::cta.b64 _, [%0], %1;" ::"r"(bar), "r"(bytes) : "memory"); }
__device__ __forceinline__ void mbar_arrive(uint32_t bar) { asm volatile("mbarrier.arrive.shared::cta.b64 _, [%0];" ::"r"(bar) : "memory"); }
__device__ __forceinline__ void mbar_wait(uint32_t bar, uint32_t parity) {
    uint32_t ok; int n = 0;
    do {
        asm volatile("{\n.reg .pred p;\nmbarrier.try_wait.parity.shared::cta.b64 p, [%1], %2;\nselp.u32 %0, 1, 0, p;\n}" : "=r"(ok) : "r"(bar), "r"(parity) : "memory");
        if (++n > SPIN_LIMIT) __trap();
    } while (!ok);
}
__device__ __forceinline__ void mbar_wait_c(uint32_t bar, uint32_t parity) {
    asm volatile("{\n.reg .pred p;\nWL:\nmbarrier.try_wait.parity.shared::cta.b64 p, [%0], %1;\n@!p bra WL;\n}" ::"r"(bar), "r"(parity) : "memory");
}
__device__ __forceinline__ void mbar_wait_cluster(uint32_t bar, uint32_t parity) {
    uint32_t ok; int n = 0;
    do {
        asm volatile("{\n.reg .pred p;\nmbarrier.try_wait.parity.acquire.cluster.shared::cta.b64 p, [%1], %2;\nselp.u32 %0, 1, 0, p;\n}" : "=r"(ok) : "r"(bar), "r"(parity) : "memory");
        if (++n > SPIN_LIMIT) __trap();
    } while (!ok);
}
__device__ __forceinline__ void warp_arrive(uint32_t bar) {
    __syncwarp();
    asm volatile("{\n.reg .pred p;\nelect.sync _|p, 0xffffffff;\n@p mbarrier.arrive.shared::cta.b64 _, [%0];\n}" ::"r"(bar) : "memory");
}
__device__ __forceinline__ int opaque(int v) { return __shfl_sync(~0u, v, 0); }
__device__ __forceinline__ int fresh_tid() { int v; asm volatile("mov.u32 %0, %%tid.x;" : "=r"(v)); return v; }
__device__ __forceinline__ void bar_sync(int id, int n) { asm volatile("bar.sync %0, %1;" ::"r"(id), "r"(n) : "memory"); }
__device__ __forceinline__ void bar_arrive(int id, int n) { asm volatile("bar.arrive %0, %1;" ::"r"(id), "r"(n) : "memory"); }
__device__ __forceinline__ void fence_async_smem() { asm volatile("fence.proxy.async.shared::cta;" ::: "memory"); }
__device__ __forceinline__ void fence_async_global() { asm volatile("fence.proxy.async.global;" ::: "memory"); }
__device__ __forceinline__ void fence_gpu() { asm volatile("fence.release.gpu;" ::: "memory"); }
__device__ __forceinline__ void tma3(uint32_t dst, const CUtensorMap* m, int c0, int c1, int c2, uint32_t bar) {
    asm volatile("cp.async.bulk.tensor.3d.shared::cluster.global.mbarrier::complete_tx::bytes [%0], [%1, {%3, %4, %5}], [%2];"
                 ::"r"(dst), "l"(m), "r"(bar), "r"(c0), "r"(c1), "r"(c2) : "memory");
}
__device__ __forceinline__ void bulk_load(uint32_t dst, const void* src, uint32_t bytes, uint32_t bar) {
    asm volatile("cp.async.bulk.shared::cluster.global.mbarrier::complete_tx::bytes [%0], [%1], %2, [%3];" ::"r"(dst), "l"(src), "r"(bytes), "r"(bar) : "memory");
}
__device__ __forceinline__ void expect_e(uint32_t bar, uint32_t bytes) {
    asm volatile("{\n.reg .pred p;\nelect.sync _|p, 0xffffffff;\n@p mbarrier.arrive.expect_tx.shared::cta.b64 _, [%0], %1;\n}" ::"r"(bar), "r"(bytes) : "memory");
}
__device__ __forceinline__ void tma3_e(uint32_t dst, const CUtensorMap* m, int c0, int c1, int c2, uint32_t bar) {
    asm volatile("{\n.reg .pred p;\nelect.sync _|p, 0xffffffff;\n@p cp.async.bulk.tensor.3d.shared::cluster.global.mbarrier::complete_tx::bytes [%0], [%1, {%3, %4, %5}], [%2];\n}"
                 ::"r"(dst), "l"(m), "r"(bar), "r"(c0), "r"(c1), "r"(c2) : "memory");
}
__device__ __forceinline__ void bulk_e(uint32_t dst, const void* src, uint32_t bytes, uint32_t bar) {
    asm volatile("{\n.reg .pred p;\nelect.sync _|p, 0xffffffff;\n@p cp.async.bulk.shared::cluster.global.mbarrier::complete_tx::bytes [%0], [%1], %2, [%3];\n}"
                 ::"r"(dst), "l"(src), "r"(bytes), "r"(bar) : "memory");
}
__device__ __forceinline__ void init_e(uint32_t bar, int cnt) {
    asm volatile("{\n.reg .pred p;\nelect.sync _|p, 0xffffffff;\n@p mbarrier.init.shared::cta.b64 [%0], %1;\n}" ::"r"(bar), "r"(cnt) : "memory");
}
__device__ __forceinline__ void l2_prefetch_e(const void* src, uint32_t bytes) {
    asm volatile("{\n.reg .pred p;\nelect.sync _|p, 0xffffffff;\n@p cp.async.bulk.prefetch.L2.global [%0], %1;\n}" ::"l"(src), "r"(bytes) : "memory");
}
__device__ __forceinline__ uint32_t ld_relaxed(const uint32_t* p) { uint32_t v; asm volatile("ld.relaxed.gpu.global.u32 %0, [%1];" : "=r"(v) : "l"(p) : "memory"); return v; }
__device__ __forceinline__ void st_relaxed(uint32_t* p, uint32_t v) { asm volatile("st.relaxed.gpu.global.u32 [%0], %1;" ::"l"(p), "r"(v) : "memory"); }
__device__ __forceinline__ uint4 ld_relaxed4(const uint4* p) { uint4 v; asm volatile("ld.relaxed.gpu.global.v4.u32 {%0,%1,%2,%3}, [%4];" : "=r"(v.x), "=r"(v.y), "=r"(v.z), "=r"(v.w) : "l"(p) : "memory"); return v; }
__device__ __forceinline__ void st_relaxed4(uint4* p, uint4 v) { asm volatile("st.relaxed.gpu.global.v4.u32 [%0], {%1,%2,%3,%4};" ::"l"(p), "r"(v.x), "r"(v.y), "r"(v.z), "r"(v.w) : "memory"); }
__device__ __forceinline__ uint4 ldg_nc4(const void* p) { uint4 v; asm volatile("ld.global.nc.L1::no_allocate.v4.u32 {%0,%1,%2,%3}, [%4];" : "=r"(v.x), "=r"(v.y), "=r"(v.z), "=r"(v.w) : "l"(p)); return v; }
__device__ __forceinline__ uint32_t ldg_nc(const void* p) { uint32_t v; asm volatile("ld.global.nc.u32 %0, [%1];" : "=r"(v) : "l"(p)); return v; }
__device__ __forceinline__ uint32_t ld_acquire(const uint32_t* p) { uint32_t v; asm volatile("ld.acquire.gpu.global.u32 %0, [%1];" : "=r"(v) : "l"(p) : "memory"); return v; }
__device__ __forceinline__ uint4 lds4(uint32_t a) { uint4 v; asm volatile("ld.shared.v4.u32 {%0,%1,%2,%3}, [%4];" : "=r"(v.x), "=r"(v.y), "=r"(v.z), "=r"(v.w) : "r"(a) : "memory"); return v; }
__device__ __forceinline__ float2 lds2f(uint32_t a) { float2 v; asm volatile("ld.shared.v2.f32 {%0,%1}, [%2];" : "=f"(v.x), "=f"(v.y) : "r"(a) : "memory"); return v; }
__device__ __forceinline__ uint32_t lds1(uint32_t a) { uint32_t v; asm volatile("ld.shared.u32 %0, [%1];" : "=r"(v) : "r"(a) : "memory"); return v; }
__device__ __forceinline__ void sts4(uint32_t a, uint4 v) { asm volatile("st.shared.v4.u32 [%0], {%1,%2,%3,%4};" ::"r"(a), "r"(v.x), "r"(v.y), "r"(v.z), "r"(v.w) : "memory"); }
__device__ __forceinline__ void sts2(uint32_t a, uint32_t x, uint32_t y) { asm volatile("st.shared.v2.u32 [%0], {%1,%2};" ::"r"(a), "r"(x), "r"(y) : "memory"); }
__device__ __forceinline__ void sts1(uint32_t a, uint32_t v) { asm volatile("st.shared.u32 [%0], %1;" ::"r"(a), "r"(v) : "memory"); }
__device__ __forceinline__ void stsm4(uint32_t a, uint32_t r0, uint32_t r1, uint32_t r2, uint32_t r3) {
    asm volatile("stmatrix.sync.aligned.m8n8.x4.shared.b16 [%0], {%1,%2,%3,%4};" ::"r"(a), "r"(r0), "r"(r1), "r"(r2), "r"(r3));
}
__device__ __forceinline__ uint32_t pack2(float lo, float hi) { uint32_t r; asm("cvt.rn.bf16x2.f32 %0, %1, %2;" : "=r"(r) : "f"(hi), "f"(lo)); return r; }
__device__ __forceinline__ uint32_t pack2_relu(float lo, float hi) { uint32_t r; asm("cvt.rn.relu.bf16x2.f32 %0, %1, %2;" : "=r"(r) : "f"(hi), "f"(lo)); return r; }
__device__ __forceinline__ uint32_t hfma2(uint32_t a, uint32_t b, uint32_t c) { uint32_t r; asm("fma.rn.bf16x2 %0, %1, %2, %3;" : "=r"(r) : "r"(a), "r"(b), "r"(c)); return r; }
__device__ __forceinline__ uint32_t hmul2(uint32_t a, uint32_t b) { uint32_t r; asm("mul.rn.bf16x2 %0, %1, %2;" : "=r"(r) : "r"(a), "r"(b)); return r; }
__device__ __forceinline__ float bf_lo(uint32_t v) { return __uint_as_float(v << 16); }
__device__ __forceinline__ float bf_hi(uint32_t v) { return __uint_as_float(v & 0xFFFF0000u); }
__device__ __forceinline__ float bf_round(float v) { return bf_lo(pack2(v, 0.f)); }
__device__ __forceinline__ float ex2(float x) { float r; asm("ex2.approx.ftz.f32 %0, %1;" : "=f"(r) : "f"(x)); return r; }
__device__ __forceinline__ void mma16816(float* d, uint32_t a0, uint32_t a1, uint32_t a2, uint32_t a3, uint32_t b0, uint32_t b1) {
    asm("mma.sync.aligned.m16n8k16.row.col.f32.bf16.bf16.f32 {%0,%1,%2,%3}, {%4,%5,%6,%7}, {%8,%9}, {%0,%1,%2,%3};"
        : "+f"(d[0]), "+f"(d[1]), "+f"(d[2]), "+f"(d[3]) : "r"(a0), "r"(a1), "r"(a2), "r"(a3), "r"(b0), "r"(b1));
}
__device__ __forceinline__ void mma16816_first(float* d, uint32_t a0, uint32_t a1, uint32_t a2, uint32_t a3, uint32_t b0, uint32_t b1) {
    asm volatile("mma.sync.aligned.m16n8k16.row.col.f32.bf16.bf16.f32 {%0,%1,%2,%3}, {%4,%5,%6,%7}, {%8,%9}, {%10,%10,%10,%10};"
        : "=f"(d[0]), "=f"(d[1]), "=f"(d[2]), "=f"(d[3]) : "r"(a0), "r"(a1), "r"(a2), "r"(a3), "r"(b0), "r"(b1), "f"(0.f));
}
__device__ __forceinline__ void mma16816_v(float* d, uint32_t a0, uint32_t a1, uint32_t a2, uint32_t a3, uint32_t b0, uint32_t b1) {
    asm volatile("mma.sync.aligned.m16n8k16.row.col.f32.bf16.bf16.f32 {%0,%1,%2,%3}, {%4,%5,%6,%7}, {%8,%9}, {%0,%1,%2,%3};"
        : "+f"(d[0]), "+f"(d[1]), "+f"(d[2]), "+f"(d[3]) : "r"(a0), "r"(a1), "r"(a2), "r"(a3), "r"(b0), "r"(b1));
}
__device__ __forceinline__ void mma1688(float* d, uint32_t a0, uint32_t a1, uint32_t b0) {
    asm("mma.sync.aligned.m16n8k8.row.col.f32.bf16.bf16.f32 {%0,%1,%2,%3}, {%4,%5}, {%6}, {%0,%1,%2,%3};"
        : "+f"(d[0]), "+f"(d[1]), "+f"(d[2]), "+f"(d[3]) : "r"(a0), "r"(a1), "r"(b0));
}
__device__ __forceinline__ void ldsm4(uint32_t a, uint32_t* r) {
    asm volatile("ldmatrix.sync.aligned.m8n8.x4.shared.b16 {%0,%1,%2,%3}, [%4];" : "=r"(r[0]), "=r"(r[1]), "=r"(r[2]), "=r"(r[3]) : "r"(a));
}
__device__ __forceinline__ void ldsm4t(uint32_t a, uint32_t* r) {
    asm volatile("ldmatrix.sync.aligned.m8n8.x4.trans.shared.b16 {%0,%1,%2,%3}, [%4];" : "=r"(r[0]), "=r"(r[1]), "=r"(r[2]), "=r"(r[3]) : "r"(a));
}
__device__ __forceinline__ float rcp(float x) { float r; asm("rcp.approx.ftz.f32 %0, %1;" : "=f"(r) : "f"(x)); return r; }
__device__ __forceinline__ uint2 ld_relaxed2(const void* p) { uint2 v; asm volatile("ld.relaxed.gpu.global.v2.u32 {%0,%1}, [%2];" : "=r"(v.x), "=r"(v.y) : "l"(p) : "memory"); return v; }
__device__ __forceinline__ void st_relaxed2(void* p, uint32_t x, uint32_t y) { asm volatile("st.relaxed.gpu.global.v2.u32 [%0], {%1,%2};" ::"l"(p), "r"(max(x, 1u)), "r"(max(y, 1u)) : "memory"); }
__host__ __device__ constexpr uint64_t dconst(uint32_t lbo, uint32_t sbo, uint32_t swz) {
    return ((uint64_t)(lbo >> 4) << 16) | ((uint64_t)(sbo >> 4) << 32) | ((uint64_t)swz << 62);
}
__device__ __forceinline__ uint32_t mkdesc(uint32_t addr, uint64_t c) { return (uint32_t)c | ((addr & 0x3FFFF) >> 4); }
#define WG_FENCE() asm volatile("wgmma.fence.sync.aligned;" ::: "memory")
#define WG_COMMIT() asm volatile("wgmma.commit_group.sync.aligned;" ::: "memory")
#define WG_WAIT(n) asm volatile("wgmma.wait_group.sync.aligned %0;" ::"n"(n) : "memory")
template <int N> __device__ __forceinline__ void reg_fence(float* d) {
#pragma unroll
    for (int i = 0; i < N; i++) asm volatile("" : "+f"(d[i])::"memory");
}
template <int N> __device__ __forceinline__ void reg_def(float* d) {
#pragma unroll
    for (int i = 0; i < N; i++) asm volatile("" : "=f"(d[i]));
}
template <int N> __device__ __forceinline__ void reg_def(uint32_t* d) {
#pragma unroll
    for (int i = 0; i < N; i++) asm volatile("" : "=r"(d[i]));
}
__device__ __forceinline__ bool is_unset(uint4 v) { return min(min(v.x, v.y), min(v.z, v.w)) == 0u; }
__device__ __forceinline__ uint4 nz4(uint32_t a, uint32_t b, uint32_t c, uint32_t d) { return make_uint4(max(a, 1u), max(b, 1u), max(c, 1u), max(d, 1u)); }
__device__ __forceinline__ void wait_flags(const uint32_t* p, uint32_t target, uint32_t mask) {
    int n = 0;
    while (~__ballot_sync(~0u, (int)(ld_relaxed(p) - target) >= 0) & mask) { if (++n > SPIN_LIMIT) __trap(); }
    asm volatile("fence.acquire.gpu;" ::: "memory");
}
__device__ __forceinline__ float silu_bf(uint32_t cbits) {
    const float c = __uint_as_float(cbits << 16);
    return bf_round(__fdividef(c, 1.f + fminf(ex2(-1.4426950408889634f * c), 1e30f)));
}
__device__ __forceinline__ void gemv_part(uint32_t wmbuf, int npanel, int wp, int lane) {
    const uint32_t wa = wmbuf + wp * 512 + (8 * (lane >> 4) + (lane & 7)) * 32 + ((lane >> 3) & 1) * 16;
    uint2 B[4];
#pragma unroll
    for (int i = 0; i < 4; i++) { const float2 v = lds2f(wmbuf + 28672 + (wp + 8 * i) * 32 + (lane & 3) * 8); B[i] = make_uint2(__float_as_uint(v.x), __float_as_uint(v.y)); }
#pragma unroll 1
    for (int pn = 0; pn < npanel; pn++) {
        float d[4] = {};
        uint32_t A[16];
#pragma unroll
        for (int i = 0; i < 4; i++) ldsm4t(wa + pn * 14336 + (i < 3 || wp < 4 ? i : 0) * 4096, A + 4 * i);
#pragma unroll
        for (int i = 0; i < 4; i++) mma16816(d, A[4 * i], A[4 * i + 1], A[4 * i + 2], A[4 * i + 3], B[i].x, B[i].y);
        if ((lane & 3) == 0) {
            sts1(wmbuf + 29696 + (wp * 32 + pn * 16 + (lane >> 2)) * 4, __float_as_uint(d[0]));
            sts1(wmbuf + 29696 + (wp * 32 + pn * 16 + 8 + (lane >> 2)) * 4, __float_as_uint(d[2]));
        }
    }
}
__device__ __forceinline__ int pass_f(int fs, int ps) { return 224 * fs + ((fs & 1) ? (ps == 0 ? 96 : ps == 1 ? 32 : 0) : (ps == 0 ? 0 : ps == 1 ? 128 : 192)); }
__device__ __forceinline__ constexpr uint32_t slot_off(int l) { return (l < 3 || l > 6 ? l : l == 6 ? 3 : l + 1) * 16384; }
__device__ __forceinline__ void ln_coeffs(float mean, float msq, uint32_t& r2, uint32_t& n2) {
    const float rs = bf_round(rsqrtf(fmaxf(msq - mean * mean, 0.f) + 1e-5f));
    r2 = pack2(rs, rs);
    n2 = pack2(-mean * rs, -mean * rs);
}

#define LOADW bulk_e(dst, g_wd + (size_t)((f >> 5) * 4 + nq) * 1792, 7168, bar);
template <int sec> __device__ __forceinline__ void ring_loader(const Params& p, uint32_t sb_, int r_, int j_, int lane) {
    const uint32_t sb = opaque(sb_);
    const int r = opaque(r_), j = opaque(j_), nq = j >> 1, fs = 4 * (j & 1) + nq;
    const int fa = pass_f(fs, 0), fb = pass_f(fs, 1), fc = pass_f(fs, 2);
#define BAR(i) (sb + M_BAR + 8 * (i))
#define kh (j & 1)
            int sl = 0;
            mbar_wait(BAR(B_PUB + 2), 0);
            wait_flags(g_flag + (8 * r + j) * 128 + 96 + lane, lds1(sb + M_EPOCH) + 1, 0xFFFFu);
            fence_async_global();
#pragma unroll 1
            for (int s = 0; s < 28; s++) {
                if (s >= PACE && s < PACE_END) mbar_wait(BAR(B_FULL + s - PACE), 0);
                const int ps = s < 14 ? 0 : s < 21 ? 1 : 2;
                const uint32_t half = ps < 2 ? 8192 : 4096;
                mbar_wait(BAR(B_EMPTY + sl), (s >= 7 && s < 14) || s >= 21);
                expect_e(BAR(B_FULL + sl), half);
                tma3_e(sb + slot_off(sl) + sec * half, &p.ga + 2 * ps + sec, 0, ps ? 64 * sl : 32 * s, ps == 0 ? fa >> 6 : ps == 1 ? fb >> 6 : fc >> 5, BAR(B_FULL + sl));
                sl = sl == 6 ? 0 : sl + 1;
            }
            if (!sec) PROFH(3);
#pragma unroll 1
            for (int e = 0; e < 4; e++) {
                const uint32_t dst = sb + slot_off(e) + sec * 8192, bar = BAR(B_FULL + e);
                const int f = (e < 2 ? fa + 64 * e : e == 2 ? fb : fc) + 32 * sec;
                mbar_wait(BAR(B_EMPTY + e), 0);
                expect_e(bar, e == 3 && sec ? 0 : 7168);
                if (!(e == 3 && sec)) { LOADW }
            }
            sl = 4;
            int e = 4;
#pragma unroll 1
            for (int grp = 0; grp < 9; grp++) {
                const int ps = grp >= 6 ? 2 : grp >= 3 ? 1 : 0;
                int sidx = grp - 3 * ps;
                if (sec && sidx == 0) { mbar_wait(BAR(B_HRDY + ps), 0); fence_async_global(); }
                sidx += sidx >= nq;
                int f = pass_f(4 * kh + sidx, ps);
#pragma unroll 1
                for (int k = 4 >> ps; k > 0; k--, e++, f += 32) {
                    const uint32_t dst = sb + slot_off(sl), bar = BAR(B_FULL + sl);
                    mbar_wait(BAR(B_EMPTY + sl), e >= 12 && e < 24);
                    if (e < WIN_END && e >= WIN) mbar_wait(BAR(B_FULL + (sl >= WIN ? sl - WIN : sl + 12 - WIN)), e - WIN >= 12);
                    expect_e(bar, sec ? 8192 : 7168);
                    if (!sec) { LOADW }
                    else bulk_e(dst + 8192, g_h2 + (size_t)r * (224 * 512) + f * 64, 8192, bar);
                    sl = sl == 11 ? 0 : sl + 1;
                }
            }
            if (!sec) PROFH(4);
}

__global__ void __cluster_dims__(2, 1, 1) __launch_bounds__(384, 1) fused_block_kernel(const __grid_constant__ Params p) {
    extern __shared__ __align__(1024) unsigned char smem[];
    const uint32_t sb = (uint32_t)__cvta_generic_to_shared(smem);
    const int tid = threadIdx.x, lane = tid & 31, warp = __shfl_sync(~0u, tid >> 5, 0);
    const int m = blockIdx.x >> 1;
    int r, nq;
    {
        int g, i;
        if (m < MAP_S) { g = m < 4 ? 15 : 16; i = m & 3; }
        else if (m < MAP_S + 32) { g = (m - MAP_S) & 7; i = (m - MAP_S) >> 3; }
        else if (m < MAP_S + 60) { i = (m - MAP_S - 32) / 7; g = 8 + (m - MAP_S - 32) - 7 * i; }
        else { g = 16; i = m & 3; }
        r = g; nq = i;
    }
    const int j = opaque(2 * nq + (blockIdx.x & 1)), b = 8 * r + j, fs = 4 * kh + nq;
    const uint32_t sc = r == 16;
    if (lane == 0 && warp < 9 && warp != 6 && warp != 7) {
        const int i0 = warp == 8 ? 0 : 8 + 8 * warp, cnt = warp == 0 || warp == 8 ? 1 : warp < 3 ? 2 : 8;
#pragma unroll
        for (int k = 0; k < 8; k++) if (i0 + k != B_WMFULL) mbar_init(BAR(i0 + k), cnt);
        asm volatile("fence.mbarrier_init.release.cluster;" ::: "memory");
        fence_async_smem();
    }

    if (warp < 8) {
        const int w = warp >> 2, wi = warp & 3;
#define COORDS const int t = fresh_tid() & 127, lane = t & 31, q = lane & 3, lr = lane >> 2, ra = 64 * w + 16 * wi + lr; \
        const uint32_t lx = (lane >> 4) ^ (lane & 7), mrow = (64 * w + 16 * wi + ((lane >> 3) & 1) * 8 + (lane & 7)) * 128; \
        (void)q; (void)lr; (void)ra; (void)lx; (void)mrow;
        const int sid = 2 * (j & 3) + w;
#define RUN(k) (!sc || sid == (k))
#define WAIT(i, par) mbar_wait_c(BAR(i), (par) | sc)
        constexpr uint64_t DB128 = dconst(4096, 1024, 1);
        bar_arrive(9, 384);
        bar_sync(0, 384);
        asm volatile("barrier.cluster.arrive.relaxed.aligned;" ::: "memory");
        asm volatile("setmaxnreg.inc.sync.aligned.u32 224;");
        PROFC(0);
        uint32_t xr[16];
        {
            COORDS
            uint32_t h[112];
            if (RUN(0)) {
                float ds[4] = {}, da[2][4] = {}, db[2][4] = {};
                const uint32_t ONE2 = 0x3F803F80u;
                if (kh == 0) { WAIT(B_WMFULL, 0); gemv_part(sb + OFF_Y + HALF, 1, warp, lane); warp_arrive(BAR(B_GEMV)); }
#pragma unroll
                for (int kb = 0; kb < 7; kb++) {
                    WAIT(B_XFULL + kb, 0);
#pragma unroll
                    for (int k4 = 0; k4 < 4; k4++) ldsm4(sb + OFF_X + mrow + kb * 16384 + (((2 * k4) ^ lx) << 4), h + 16 * kb + 4 * k4);
#pragma unroll
                    for (int k4 = 0; k4 < 4; k4++) {
                        const uint32_t* f = h + 16 * kb + 4 * k4;
                        mma16816(ds, f[0], f[1], f[2], f[3], ONE2, ONE2);
                        mma1688(da[0], f[0], f[1], f[0]); mma1688(db[0], f[0], f[1], f[1]);
                        mma1688(da[1], f[2], f[3], f[2]); mma1688(db[1], f[2], f[3], f[3]);
                    }
                }
#pragma unroll
                for (int i = 0; i < 4; i++) {
                    const int ch = 7 * j + 2 * i + (lane >> 4);
                    ldsm4(sb + OFF_X + mrow + (ch >> 3) * 16384 + (((ch ^ lane) & 7) << 4), xr + 4 * i);
                }
                warp_arrive(BAR(B_XFREE));
                float qa = (lr & 1) ? da[0][1] + da[1][1] : da[0][0] + da[1][0];
                float qb = (lr & 1) ? db[0][3] + db[1][3] : db[0][2] + db[1][2];
                const int src = (lane & ~3) | (lr >> 1);
                qa = __shfl_sync(~0u, qa, src);
                qb = __shfl_sync(~0u, qb, src);
                uint32_t ra2, na2, rb2, nb2;
                ln_coeffs(ds[0] * (1.f / DM), qa * (1.f / DM), ra2, na2);
                ln_coeffs(ds[2] * (1.f / DM), qb * (1.f / DM), rb2, nb2);
#pragma unroll
                for (int i = 0; i < 112; i += 2) { h[i] = hfma2(h[i], ra2, na2); h[i + 1] = hfma2(h[i + 1], rb2, nb2); }
                if (kh == 1) { WAIT(B_WMFULL, 0); gemv_part(sb + OFF_Y + HALF, 2, warp, lane); warp_arrive(BAR(B_GEMV)); }
            } else { reg_def<112>(h); reg_def<16>(xr); }
            PROFC(1);
            if (RUN(1)) {
                float ak[28], av[28], aq[28];
                uint32_t kp[14], vp[14];
                const uint32_t bk0 = mkdesc(sb + OFF_Y, DB128) + kh, bv0 = mkdesc(sb + OFF_Y + HALF, DB128) + kh, bq0 = mkdesc(sb + OFF_X, DB128) + kh;
                uint32_t* kvg = g_kv + (size_t)(b * 2) * 3584 + (8 * w + 2 * wi) * 224 + lane;
                WAIT(B_FULLK, 0);
                WAIT(B_MOD1, 0);
                PROFC(2);
                reg_def<28>(ak);
#pragma unroll
                for (int g4 = 0; g4 < 4; g4++) {
#pragma unroll
                    for (int ks = 7 * g4; ks < 7 * g4 + 7; ks++) {
                        const uint4 st = *(const uint4*)(smem + M_ST + ks * 64 + q * 16);
                        h[4 * ks] = hfma2(h[4 * ks], st.x, st.y); h[4 * ks + 1] = hfma2(h[4 * ks + 1], st.x, st.y);
                        h[4 * ks + 2] = hfma2(h[4 * ks + 2], st.z, st.w); h[4 * ks + 3] = hfma2(h[4 * ks + 3], st.z, st.w);
                    }
                    WG_FENCE();
#pragma unroll
                    for (int ks = 7 * g4; ks < 7 * g4 + 7; ks++) wgmma_rs_56<DB128>(ak, h[4 * ks], h[4 * ks + 1], h[4 * ks + 2], h[4 * ks + 3], bk0 + ks * 128, ks != 0);
                }
                WG_COMMIT();
                PROFC(3);
                WAIT(B_FULLV, 0);
                reg_def<28>(av);
                WG_FENCE();
#pragma unroll
                for (int ks = 0; ks < 8; ks++) wgmma_rs_56<DB128>(av, h[4 * ks], h[4 * ks + 1], h[4 * ks + 2], h[4 * ks + 3], bv0 + ks * 128, ks != 0);
                WG_COMMIT();
                WG_WAIT(1);
                reg_fence<28>(ak);
#pragma unroll
                for (int g = 0; g < 7; g++) {
                    kp[2 * g] = pack2(ak[4 * g], ak[4 * g + 1]); kp[2 * g + 1] = pack2(ak[4 * g + 2], ak[4 * g + 3]);
                    kvg[g * 32] = kp[2 * g]; kvg[224 + g * 32] = kp[2 * g + 1];
                }
                warp_arrive(BAR(B_PUB));
                PROFC(4);
                WG_FENCE();
#pragma unroll
                for (int ks = 8; ks < 28; ks++) wgmma_rs_56<DB128>(av, h[4 * ks], h[4 * ks + 1], h[4 * ks + 2], h[4 * ks + 3], bv0 + ks * 128, 1);
                WG_COMMIT();
                WAIT(B_FULLQ, 0);
                reg_def<28>(aq);
                WG_FENCE();
#pragma unroll
                for (int ks = 0; ks < 8; ks++) wgmma_rs_56<DB128>(aq, h[4 * ks], h[4 * ks + 1], h[4 * ks + 2], h[4 * ks + 3], bq0 + ks * 128, ks != 0);
                WG_COMMIT();
                WG_WAIT(1);
                reg_fence<28>(av);
#pragma unroll
                for (int g = 0; g < 7; g++) {
                    vp[2 * g] = pack2(av[4 * g], av[4 * g + 1]); vp[2 * g + 1] = pack2(av[4 * g + 2], av[4 * g + 3]);
                    kvg[3584 + g * 32] = vp[2 * g]; kvg[3584 + 224 + g * 32] = vp[2 * g + 1];
                }
                warp_arrive(BAR(B_PUB + 1));
                PROFC(5);
                WG_FENCE();
#pragma unroll
                for (int ks = 8; ks < 28; ks++) wgmma_rs_56<DB128>(aq, h[4 * ks], h[4 * ks + 1], h[4 * ks + 2], h[4 * ks + 3], bq0 + ks * 128, 1);
                WG_COMMIT();
                WAIT(B_PUB + 1, 0);
                const uint32_t ko = sb + OFF_Y + Y_KOWN + (8 * w + 2 * wi) * 896 + lane * 4;
                const uint32_t qo = sb + OFF_Y + Y_Q + (8 * w + 2 * wi) * 1024 + lane * 4;
#pragma unroll
                for (int g = 0; g < 7; g++) {
                    sts1(ko + g * 128, kp[2 * g]); sts1(ko + 896 + g * 128, kp[2 * g + 1]);
                    sts1(ko + (Y_VOWN - Y_KOWN) + g * 128, vp[2 * g]); sts1(ko + (Y_VOWN - Y_KOWN) + 896 + g * 128, vp[2 * g + 1]);
                }
                WG_WAIT(0);
                reg_fence<28>(aq);
                __syncwarp();
                if (lane < 3 && w == 1) mbar_arrive(BAR(B_EMPTY + lane));
#pragma unroll
                for (int g = 0; g < 7; g++) {
                    const uint32_t q0 = pack2(aq[4 * g], aq[4 * g + 1]), q1 = pack2(aq[4 * g + 2], aq[4 * g + 3]);
                    if (g == 3) {
                        sts1(qo + 3 * 128, q < 2 ? q0 : 0u); sts1(qo + 1024 + 3 * 128, q < 2 ? q1 : 0u);
                        sts1(qo + 4 * 128, q < 2 ? 0u : q0); sts1(qo + 1024 + 4 * 128, q < 2 ? 0u : q1);
                    } else {
                        const int ch = g < 3 ? g : g + 1;
                        sts1(qo + ch * 128, q0); sts1(qo + 1024 + ch * 128, q1);
                    }
                }
                if (!sc) bar_sync(3, 256);
            }
        }
        PROFC(6);
        WAIT(B_KRFULL, 0);
        PROFC(7);
        if (RUN(2)) {
#pragma unroll 1
            for (int hf = sc; hf < 2; hf++) {
                COORDS
                float s[136];
                float na = 0.f, nb = 0.f;
                const float CS = 0.18898223650461361f * 1.4426950408889634f;
                const int kg0 = 8 * hf + 2 * wi;
                const int pmin = 16 - 8 * r - 4 * hf - wi;
                const float NEG = __int_as_float(0xFF800000);
                {
                    uint32_t F[8];
                    const uint32_t qa = sb + OFF_Y + Y_Q + (kg0 + ((lane >> 3) & 1)) * 1024 + (4 * w + (lane >> 4)) * 128 + (lane & 7) * 16;
                    ldsm4(qa, F); ldsm4(qa + 256, F + 4);
                    uint32_t ka = sb + OFF_Y + Y_K + kg0 * 896 + (3 * w + (lane >> 3)) * 128 + (lane & 7) * 16;
#pragma unroll
                    for (int g = 0; g < 34; g++) {
                        uint32_t B[4];
                        if (g >= 12 && g % 4 == 0) ka += __float_as_uint(s[4 * (g - 12)]) & p.zero;
                        ldsm4(ka + g * 896, B);
                        mma16816_first(s + 4 * g, F[0], F[1], F[2], F[3], B[0], B[1]);
                        mma16816_v(s + 4 * g, F[4], F[5], F[6], F[7], B[2], B[3]);
                    }
                    const bool c0 = 2 * q > lr, c1 = 2 * q + 1 > lr;
                    if (!c0) { s[0] = NEG; s[6] = NEG; }
                    if (!c1) { s[1] = NEG; s[7] = NEG; }
                    s[2] = NEG; s[3] = NEG;
                    if (c0) { s[128] = NEG; s[134] = NEG; }
                    if (c1) { s[129] = NEG; s[135] = NEG; }
                    s[132] = NEG; s[133] = NEG;
                    float ma = NEG, mb = NEG;
#pragma unroll
                    for (int pp = 0; pp < 17; pp++) {
                        const float* e = s + 8 * pp;
                        const float bias = pp < pmin ? NEG : 0.f;
                        ma = fmaxf(ma, fmaxf(fmaxf(e[0], e[1]), fmaxf(e[4], e[5])) + bias);
                        mb = fmaxf(mb, fmaxf(fmaxf(e[2], e[3]), fmaxf(e[6], e[7])) + bias);
                    }
                    ma = fmaxf(ma, __shfl_xor_sync(~0u, ma, 1)); mb = fmaxf(mb, __shfl_xor_sync(~0u, mb, 1));
                    ma = fmaxf(ma, __shfl_xor_sync(~0u, ma, 2)); mb = fmaxf(mb, __shfl_xor_sync(~0u, mb, 2));
                    na = -ma * CS; nb = -mb * CS;
                }
                PROFC(8 + 3 * hf);
                {
                    WAIT(B_VRFULL, 0);
                    float o[16] = {}, rs[4] = {};
                    uint32_t pk[2];
                    const uint32_t va = sb + OFF_Y + Y_VR + (kg0 + ((lane >> 3) & 1)) * 896 + (3 * w + (lane >> 4)) * 128 + (lane & 7) * 16;
#pragma unroll
                    for (int pp = 0; pp < 17; pp++) {
                        uint32_t B[8];
                        const uint32_t v = va + pp * 1792 + (pp == 16 || (pp >= 9 && kg0 + 2 * pp >= 32) ? Y_VOWN - 32 * 896 : 0);
                        ldsm4t(v, B); ldsm4t(v + 256, B + 4);
                        float e[8];
                        const float bias = __uint_as_float((pp < pmin ? 0xFF800000u : 0u) | ((pp < 2 ? B[0] : pk[pp & 1]) & p.zero));
#pragma unroll
                        for (int i = 0; i < 8; i++) e[i] = ex2(fmaf(s[8 * pp + i], CS, ((i & 2) ? nb : na) + bias));
                        const uint32_t p0 = pack2(e[0], e[1]), p1 = pack2(e[2], e[3]), p2 = pack2(e[4], e[5]), p3 = pack2(e[6], e[7]);
                        pk[pp & 1] = p3;
                        mma16816(rs, p0, p1, p2, p3, 0x3F803F80u, 0x3F803F80u);
#pragma unroll
                        for (int g = 0; g < 4; g++) mma16816(o + 4 * g, p0, p1, p2, p3, B[2 * g], B[2 * g + 1]);
                    }
                    PROFC(9 + 3 * hf);
                    const float ia = rcp(rs[0]), ib = rcp(rs[2]);
                    uint32_t* og = g_o + (size_t)(2 * r + hf) * 14336 + (7 * j + 3 * w) * 256 + wi * 64 + lane;
#pragma unroll
                    for (int g = 0; g < 4; g++) {
                        if ((g == 3 - 3 * w) ? ((q >> 1) == w) : true) {
                            og[g * 256] = pack2(o[4 * g] * ia, o[4 * g + 1] * ia);
                            og[g * 256 + 32] = pack2(o[4 * g + 2] * ib, o[4 * g + 3] * ib);
                        }
                    }
                    warp_arrive(BAR(B_PUB + 2 + hf));
                    PROFC(10 + 3 * hf);
                }
            }
        }
        uint32_t x1p[14];
        COORDS
        constexpr uint64_t DT = dconst(1024, 128, 0);
        const int tile = opaque((lds1(sb + M_EPOCH) & 1) * 34 + 2 * r + w);
        if (RUN(4)) {
            float ac[28];
            const uint32_t ad = mkdesc(sb + (w ? OFF_Y + HALF : OFF_X), DT), bd = mkdesc(sb + OFF_X + HALF, DB128) + kh;
            WAIT(B_WOFULL, 0);
            WAIT(B_MOD2, 0);
            WAIT(B_GFULL + w, 0);
            PROFC(28);
            reg_def<28>(ac);
#pragma unroll 1
            for (int u = 0; u < 4; u++) {
                if (u == 2) WAIT(B_XFULL + 2 + w, 1);
                WG_FENCE();
#pragma unroll
                for (int i = 0; i < 7; i++) wgmma_ss_56<DT, DB128>(ac, ad + (7 * u + i) * 128, bd + (7 * u + i) * 128, (u | i) != 0);
            }
            WG_COMMIT();
            WG_WAIT(0);
            reg_fence<28>(ac);
            PROFC(14);
            __syncwarp();
            if (lane < 3) mbar_arrive(BAR(B_EMPTY + 3 + lane));
            if (lane < 3 && w == 0) mbar_arrive(BAR(B_EMPTY + lane));
            float s1a = 0.f, s2a = 0.f, s1b = 0.f, s2b = 0.f;
            uint32_t* xo = g_x1 + (size_t)tile * 14336 + 7 * j * 256 + wi * 64 + lane;
#pragma unroll
            for (int g = 0; g < 7; g++) {
                const float2 ga = *(const float2*)(smem + M_G + (8 * g + 2 * q) * 4);
                x1p[2 * g] = pack2(fmaf(ga.x, ac[4 * g], bf_lo(xr[2 * g])), fmaf(ga.y, ac[4 * g + 1], bf_hi(xr[2 * g])));
                x1p[2 * g + 1] = pack2(fmaf(ga.x, ac[4 * g + 2], bf_lo(xr[2 * g + 1])), fmaf(ga.y, ac[4 * g + 3], bf_hi(xr[2 * g + 1])));
                st_relaxed(xo + g * 256, max(x1p[2 * g], 1u)); st_relaxed(xo + g * 256 + 32, max(x1p[2 * g + 1], 1u));
                const float u0 = bf_lo(x1p[2 * g]), u1 = bf_hi(x1p[2 * g]), u2 = bf_lo(x1p[2 * g + 1]), u3 = bf_hi(x1p[2 * g + 1]);
                s1a += u0 + u1; s2a += u0 * u0 + u1 * u1; s1b += u2 + u3; s2b += u2 * u2 + u3 * u3;
            }
            float ka = (q & 1) ? s2a : s1a, kb2 = (q & 1) ? s2b : s1b;
            ka += __shfl_xor_sync(~0u, (q & 1) ? s1a : s2a, 1); kb2 += __shfl_xor_sync(~0u, (q & 1) ? s1b : s2b, 1);
            const float kk = ((q & 2) ? kb2 : ka) + __shfl_xor_sync(~0u, (q & 2) ? ka : kb2, 2);
            st_relaxed((uint32_t*)g_st + ((tile * 8 + j) * 64 + 16 * wi + lr + 4 * (q & 2)) * 2 + (q & 1), max(__float_as_uint(kk), 1u));
            __syncwarp();
            if (lane < 2) mbar_arrive(BAR(B_PUB + 4 + w));
        } else reg_def<14>(x1p);
        PROFC(15);
        uint32_t h2a[32], h2b[24];
        {
            const int fa = pass_f(fs, 0), fb = pass_f(fs, 1), fc = pass_f(fs, 2);
            uint32_t* h2g = g_h2 + (size_t)r * (224 * 512) + (8 * w + 2 * wi) * 32 + lane;
            const uint32_t a0 = mkdesc(sb + OFF_Y + w * HALF, DT);
            if (RUN(3)) {
                WAIT(B_GFULL + 2 + w, 0);
                PROFC(16);
                float2 sa, sbb;
                {
                    uint2 u[16];
#pragma unroll
                    for (int i = 0; i < 16; i++) { const float2 v = lds2f(sb + OFF_X + X_STAT + w * 4096 + ((i >> 1) * 64 + 16 * wi + lr + 8 * (i & 1)) * 8); u[i] = make_uint2(__float_as_uint(v.x), __float_as_uint(v.y)); }
#pragma unroll 1
                    for (;;) {
                        uint32_t mn = ~0u;
#pragma unroll
                        for (int i = 0; i < 16; i++) mn = min(mn, min(u[i].x, u[i].y));
                        if (!__any_sync(~0u, mn == 0u) || sc) break;
#pragma unroll
                        for (int i = 0; i < 16; i++) u[i] = ld_relaxed2(g_st + (tile * 8 + (i >> 1)) * 64 + 16 * wi + lr + 8 * (i & 1));
                    }
                    sa = make_float2(0.f, 0.f); sbb = sa;
#pragma unroll
                    for (int i = 0; i < 16; i += 2) {
                        sa.x += __uint_as_float(u[i].x); sa.y += __uint_as_float(u[i].y);
                        sbb.x += __uint_as_float(u[i + 1].x); sbb.y += __uint_as_float(u[i + 1].y);
                    }
                }
                warp_arrive(BAR(B_EMPTY + 6));
                uint32_t ra2, na2, rb2, nb2;
                ln_coeffs(sa.x * (1.f / DM), sa.y * (1.f / DM), ra2, na2);
                ln_coeffs(sbb.x * (1.f / DM), sbb.y * (1.f / DM), rb2, nb2);
                const uint32_t ha = sb + OFF_Y + w * HALF + (lane >> 4) * 1024 + (2 * wi + ((lane >> 3) & 1)) * 128 + (lane & 7) * 16;
                const uint32_t sta = sb + M_ST + q * 16;
                const uint32_t* xg = g_x1 + (size_t)tile * 14336 + wi * 64 + lane;
                uint32_t x[8];
                uint4 st[2];
                auto load = [&](int s) {
                    if (s == 4) WAIT(B_XFULL + 4 + w, 1);
                    ldsm4(ha + s * 4096, x); ldsm4(ha + s * 4096 + 2048, x + 4);
                    st[0] = lds4(sta + s * 128); st[1] = lds4(sta + s * 128 + 64);
                };
                auto prep = [&](int s, uint32_t* f) {
                    while (__any_sync(~0u, min(min(min(x[0], x[1]), min(x[2], x[3])), min(min(x[4], x[5]), min(x[6], x[7]))) == 0u) && !sc) {
#pragma unroll
                        for (int i = 0; i < 8; i++) x[i] = ld_relaxed(xg + (4 * s + (i >> 1)) * 256 + (i & 1) * 32);
                    }
#pragma unroll
                    for (int i = 0; i < 2; i++) {
                        f[4 * i] = hfma2(hfma2(x[4 * i], ra2, na2), st[i].x, st[i].y); f[4 * i + 1] = hfma2(hfma2(x[4 * i + 1], rb2, nb2), st[i].x, st[i].y);
                        f[4 * i + 2] = hfma2(hfma2(x[4 * i + 2], ra2, na2), st[i].z, st[i].w); f[4 * i + 3] = hfma2(hfma2(x[4 * i + 3], rb2, nb2), st[i].z, st[i].w);
                    }
                    if (s < 13) load(s + 1);
                    stsm4(ha + s * 4096, f[0], f[1], f[2], f[3]); stsm4(ha + s * 4096 + 2048, f[4], f[5], f[6], f[7]);
                };
                float ac[128];
                uint32_t fr[3][8];
                const uint32_t bx = mkdesc(sb, DB128);
                reg_def<128>(ac);
                load(0);
                prep(0, fr[0]);
                PROFC(17);
#pragma unroll
                for (int s = 0; s < 14; s++) {
                    {
                        const uint32_t* f = fr[s % 3];
                        const uint32_t bd = bx + (slot_off(s % 7) >> 4);
                        WAIT(B_FULL + s % 7, s >= 7);
                        WG_FENCE();
                        wgmma_rs_256<DB128>(ac, f[0], f[1], f[2], f[3], bd, s != 0);
                        wgmma_rs_256<DB128>(ac, f[4], f[5], f[6], f[7], bd + 128, 1);
                        WG_COMMIT();
                        if (s < 13) prep(s + 1, fr[(s + 1) % 3]);
                        if (s > 0) { WG_WAIT(1); warp_arrive(BAR(B_EMPTY + (s - 1) % 7)); }
                    }
                }
                PROFC(18);
                fence_async_smem();
                WG_WAIT(0);
                reg_fence<128>(ac);
                warp_arrive(BAR(B_EMPTY + 6));
#pragma unroll
                for (int g = 0; g < 16; g++) {
                    h2a[2 * g] = hmul2(pack2_relu(ac[4 * g], ac[4 * g + 1]), pack2(ac[64 + 4 * g], ac[64 + 4 * g + 1]));
                    h2a[2 * g + 1] = hmul2(pack2_relu(ac[4 * g + 2], ac[4 * g + 3]), pack2(ac[64 + 4 * g + 2], ac[64 + 4 * g + 3]));
                    h2g[(fa / 8 + g) * 512] = h2a[2 * g]; h2g[(fa / 8 + g) * 512 + 32] = h2a[2 * g + 1];
                }
                warp_arrive(BAR(B_PUB + 6));
                bar_sync(1 + w, 128);
            } else reg_def<32>(h2a);
            PROFC(19);
            if (RUN(5)) {
                float ac[64];
                reg_def<64>(ac);
                const uint32_t bx = mkdesc(sb, dconst(8192, 1024, 1));
#pragma unroll kB
                for (int s = 0; s < 7; s++) {
                    WAIT(B_FULL + s, 0);
                    const uint32_t ad = a0 + s * 512, bd = bx + (slot_off(s) >> 4);
                    WG_FENCE();
#pragma unroll
                    for (int k = 0; k < 4; k++) wgmma_ss_128<DT, DB128>(ac, ad + k * 128, bd + k * 128, (s | k) != 0);
                    WG_COMMIT();
                    if (s > 0) { WG_WAIT(1); warp_arrive(BAR(B_EMPTY + s - 1)); }
                }
                WG_WAIT(0);
                reg_fence<64>(ac);
                warp_arrive(BAR(B_EMPTY + 6));
#pragma unroll
                for (int g = 0; g < 8; g++) {
                    h2b[2 * g] = hmul2(pack2_relu(ac[4 * g], ac[4 * g + 1]), pack2(ac[32 + 4 * g], ac[32 + 4 * g + 1]));
                    h2b[2 * g + 1] = hmul2(pack2_relu(ac[4 * g + 2], ac[4 * g + 3]), pack2(ac[32 + 4 * g + 2], ac[32 + 4 * g + 3]));
                    h2g[(fb / 8 + g) * 512] = h2b[2 * g]; h2g[(fb / 8 + g) * 512 + 32] = h2b[2 * g + 1];
                }
                warp_arrive(BAR(B_PUB + 7));
            } else reg_def<16>(h2b);
            PROFC(27);
            if (RUN(6)) {
                float ac[32];
                reg_def<32>(ac);
                const uint32_t bx = mkdesc(sb, dconst(4096, 512, 2));
#pragma unroll kC
                for (int s = 0; s < 7; s++) {
                    WAIT(B_FULL + s, 1);
                    const uint32_t ad = a0 + p.zero + s * 512, bd = bx + (slot_off(s) >> 4);
                    WG_FENCE();
#pragma unroll
                    for (int k = 0; k < 4; k++) wgmma_ss_64<DT, dconst(4096, 512, 2)>(ac, ad + k * 128, bd + k * 64, (s | k) != 0);
                    WG_COMMIT();
                    if (s > 0) { WG_WAIT(1); warp_arrive(BAR(B_EMPTY + s - 1)); }
                }
                WG_WAIT(0);
                reg_fence<32>(ac);
                __syncwarp();
                if (lane < 6) mbar_arrive(BAR(B_EMPTY + 6 + lane));
                PROFC(20);
#pragma unroll
                for (int g = 0; g < 4; g++) {
                    h2b[16 + 2 * g] = hmul2(pack2_relu(ac[4 * g], ac[4 * g + 1]), pack2(ac[16 + 4 * g], ac[16 + 4 * g + 1]));
                    h2b[16 + 2 * g + 1] = hmul2(pack2_relu(ac[4 * g + 2], ac[4 * g + 3]), pack2(ac[16 + 4 * g + 2], ac[16 + 4 * g + 3]));
                    h2g[(fc / 8 + g) * 512] = h2b[16 + 2 * g]; h2g[(fc / 8 + g) * 512 + 32] = h2b[16 + 2 * g + 1];
                }
                warp_arrive(BAR(B_PUB + 8));
                asm volatile("barrier.cluster.wait.aligned;" ::: "memory");
                if (lane == 0 && !sc) {
                    uint32_t rb;
                    asm volatile("mapa.shared::cluster.u32 %0, %1, %2;" : "=r"(rb) : "r"(BAR(B_PEER)), "r"(kh ^ 1));
                    asm volatile("mbarrier.arrive.relaxed.cluster.shared::cluster.b64 _, [%0];" ::"r"(rb) : "memory");
                }
            } else reg_def<8>(h2b + 16);
        }
        PROFC(21);
        if (RUN(7)) {
            float ac[56];
            reg_def<56>(ac);
            constexpr uint64_t DAN = dconst(2048, 128, 0);
            constexpr uint64_t DW = dconst(128, 512, 0);
            const uint32_t bx = mkdesc(sb, DW);
#pragma unroll
            for (int e = 0; e < 4; e++) {
                WAIT(B_FULL + e, 0);
                const uint32_t bd = bx + (slot_off(e) >> 4);
                const uint32_t* hh = e < 2 ? h2a + 16 * e : h2b + 16 * (e - 2);
                WG_FENCE();
#pragma unroll
                for (int k = 0; k < (e < 3 ? 4 : 2); k++) wgmma_rs_112<DW>(ac, hh[4 * k], hh[4 * k + 1], hh[4 * k + 2], hh[4 * k + 3], bd + (k >> 1) * 512 + (k & 1) * 16, (e | k) != 0);
                WG_COMMIT();
                if (e > 0) { WG_WAIT(1); warp_arrive(BAR(B_EMPTY + e - 1)); }
            }
            PROFC(22);
            const uint32_t ax = mkdesc(sb + 8192 + w * 1024, DAN);
#pragma unroll kG2
            for (int e = 4; e < 25; e++) {
                WAIT(B_FULL + e % 12, e >= 12 && e < 24);
                if (e == 16) PROFC(23);
                const uint32_t z = (e / 12) * p.zero;
                const uint32_t ad = ax + z + (slot_off(e % 12) >> 4), bd = bx + z + (slot_off(e % 12) >> 4);
                WG_FENCE();
                wgmma_ss_112<DAN, DW>(ac, ad, bd, 1);
                wgmma_ss_112<DAN, DW>(ac, ad + 256, bd + 16, 1);
                WG_COMMIT();
                if (e < 14) { WG_WAIT(1); warp_arrive(BAR(B_EMPTY + (e - 1) % 12)); }
            }
            mbar_wait_cluster(BAR(B_PEER), sc);
            WG_WAIT(0);
            reg_fence<56>(ac);
            PROFC(24);
            uint32_t rdst, rbar;
            asm volatile("mapa.shared::cluster.u32 %0, %1, %2;" : "=r"(rdst) : "r"(sb + OFF_Y + (5 + w) * 16384 + t * 16), "r"(kh ^ 1 ^ sc));
            asm volatile("mapa.shared::cluster.u32 %0, %1, %2;" : "=r"(rbar) : "r"(BAR(B_XCH + w)), "r"(kh ^ 1 ^ sc));
#define ACG(g, i) ac[4 * (g) + (i)]
#pragma unroll
            for (int g = 0; g < 7; g++) {
                const float v0 = kh ? ACG(g, 0) : ACG(g + 7, 0), v1 = kh ? ACG(g, 1) : ACG(g + 7, 1);
                const float v2 = kh ? ACG(g, 2) : ACG(g + 7, 2), v3 = kh ? ACG(g, 3) : ACG(g + 7, 3);
                if (!sc) asm volatile("st.async.shared::cluster.mbarrier::complete_tx::bytes.v4.f32 [%0], {%1,%2,%3,%4}, [%5];"
                             ::"r"(rdst + g * 2048), "f"(v0), "f"(v1), "f"(v2), "f"(v3), "r"(rbar) : "memory");
            }
            mbar_wait_cluster(BAR(B_XCH + w), sc);
            PROFC(25);
            bf16* og = (sc ? (bf16*)(g_h2 + 16 * 224 * 512) : p.out + (size_t)128 * r * DM) + (size_t)ra * DM + 56 * j + 2 * q;
#pragma unroll
            for (int g = 0; g < 7; g++) {
                const uint4 rv = *(const uint4*)(smem + OFF_Y + (5 + w) * 16384 + t * 16 + g * 2048);
                const float2 gb = *(const float2*)(smem + M_G + 224 + (8 * g + 2 * q) * 4);
                const float v0 = (kh ? ACG(g + 7, 0) : ACG(g, 0)) + __uint_as_float(rv.x), v1 = (kh ? ACG(g + 7, 1) : ACG(g, 1)) + __uint_as_float(rv.y);
                const float v2 = (kh ? ACG(g + 7, 2) : ACG(g, 2)) + __uint_as_float(rv.z), v3 = (kh ? ACG(g + 7, 3) : ACG(g, 3)) + __uint_as_float(rv.w);
                *(uint32_t*)(og + 8 * g) = pack2(fmaf(gb.x, v0, bf_lo(x1p[2 * g])), fmaf(gb.y, v1, bf_hi(x1p[2 * g])));
                *(uint32_t*)(og + 8 * DM + 8 * g) = pack2(fmaf(gb.x, v2, bf_lo(x1p[2 * g + 1])), fmaf(gb.y, v3, bf_hi(x1p[2 * g + 1])));
            }
        }
        PROFC(26);
        bar_sync(1 + w, 128);
        if (wi == 0) warp_arrive(BAR(B_DONE));
    } else {
        const int lane = fresh_tid() & 31;
        const bool early = kh == 0, gemv = r < 14;
        const int mcol = early ? 16 * (4 * r + nq) : 2 * DM + 32 * (4 * r + nq);
        const uint32_t wmbuf = sb + OFF_Y + HALF;
        asm volatile("setmaxnreg.dec.sync.aligned.u32 56;");
        if (warp == 9) {
#pragma unroll
            for (int i = 56; i < 64; i++) init_e(BAR(i), 1);
            fence_async_smem();
        }
        if (warp == 8) { init_e(BAR(B_WMFULL), 2); fence_async_smem(); }
        bar_arrive(0, 384);
        asm volatile("barrier.cluster.arrive.relaxed.aligned;" ::: "memory");
        uint32_t target = 0;
        if (warp == 8) {
            if (!sc) {
                expect_e(BAR(B_WMFULL), gemv ? 28672 >> early : 0);
                if (early && gemv) { tma3_e(wmbuf, &p.wm, mcol, 0, 0, BAR(B_WMFULL)); tma3_e(wmbuf + 7168, &p.wm, mcol, 224, 0, BAR(B_WMFULL)); }
#pragma unroll 1
                for (int kb = 0; kb < 7; kb++) {
                    expect_e(BAR(B_XFULL + kb), 16384);
                    tma3_e(sb + OFF_X + kb * 16384, &p.xm, 64 * kb, 128 * r, 0, BAR(B_XFULL + kb));
                }
            }
#pragma unroll 1
            for (int mt = 0; mt < 4; mt++) {
                if (mt == 1) {
                    if (!early && gemv) {
#pragma unroll 1
                        for (int k = 0; k < 4; k++) tma3_e(wmbuf + k * 7168, &p.wm, mcol + (k >> 1) * 16, (k & 1) * 224, 0, BAR(B_WMFULL));
                    }
                    bar_sync(9, 384);
                    if (sc) return;
                    mbar_wait(BAR(B_MOD1), 0);
                    mbar_wait(BAR(B_WMFREE), 0);
                }
                if (mt == 2) mbar_wait(BAR(B_XFREE), 0);
                if (mt == 3) mbar_wait(BAR(B_VRFULL), 0);
                const uint32_t bar = BAR(mt == 3 ? B_WOFULL : B_FULLK + mt), dst = sb + (mt < 2 ? OFF_Y : OFF_X) + (mt & 1) * HALF;
                const int c0 = (mt < 2 ? DM + DM * mt : 0) + 56 * j - 8 * kh;
                if (!sc) {
                    expect_e(bar, HALF);
                    tma3_e(dst, mt == 3 ? &p.wo : &p.qkv, c0, 0, 0, bar);
                    tma3_e(dst + HALF / 2, mt == 3 ? &p.wo : &p.qkv, c0, 224, 0, bar);
                }
            }
            expect_e(BAR(B_XCH), 14336);
            expect_e(BAR(B_XCH + 1), 14336);
        } else {
            if (warp == 10 && !sc) {
                l2_prefetch_e((const char*)p.wqkv + (size_t)b * 9408, 9408);
                if (lane == 0) sts1(sb + M_EPOCH, atomicAdd(&g_ticket, 1u) / NCTA);
            }
            if (warp == 11) {
#pragma unroll
                for (int i = 0; i < 8; i++) {
                    const int wd = lane + 32 * i;
                    const uint32_t cb = i < 7 ? __ldg((const uint32_t*)p.c + wd) : 0u;
                    sts1(wmbuf + 28672 + (wd >> 3) * 32 + (wd & 3) * 8 + (wd & 4), pack2(silu_bf(cb & 0xFFFFu), silu_bf(cb >> 16)));
                }
            }
            bar_sync(9, 384);
            if (sc) return;
            target = lds1(sb + M_EPOCH) + 1;
            const uint32_t tag = target & 0xFFFFu;
            if (warp == 11) {
                warp_arrive(BAR(B_WMFULL));
                mbar_wait(BAR(B_GEMV), 0);
                float sum = 0.f;
#pragma unroll
                for (int i = 0; i < 8; i++) sum += *(const float*)(smem + OFF_Y + HALF + 29696 + (i * 32 + (early ? lane & 15 : lane)) * 4);
                const uint32_t word = (pack2(sum, 0.f) << 16) | tag;
                if (gemv) {
                    uint32_t* mg = g_mod + mcol + (early ? (lane & 15) + (lane >> 4) * 4 * 6 * DM : lane);
#pragma unroll
                    for (int i = 0; i < 8; i++) if (i < 4 || !early) st_relaxed(mg + i * 6 * DM, word);
                }
                warp_arrive(BAR(B_WMFREE));
            }
            const uint4* modp = (const uint4*)g_mod + (r & 7) * (6 * DM / 4);
            const bool p2 = warp == 11;
            mbar_wait(BAR(p2 ? B_PUB : B_XFULL + 4), 0);
#pragma unroll 1
            for (int it = p2 ? 0 : warp - 9; it < (p2 ? 2 : warp - 8); it++) {
                const int i0 = lane + 32 * it, imax = p2 ? 251 : 223;
                uint4 v[4];
#pragma unroll 1
                for (int n = 0;; n++) {
                    uint32_t bad = 0;
#pragma unroll
                    for (int k = 0; k < 4; k++) {
                        const int i = min(i0 + 64 * k, imax);
                        v[k] = ld_relaxed4(modp + (i < 224 ? (p2 ? 336 : 0) + i : (i < 238 ? 14 * j + i : 14 * j + i + 322)));
                        bad |= (v[k].x ^ tag) | (v[k].y ^ tag) | (v[k].z ^ tag) | (v[k].w ^ tag);
                    }
                    if (!__any_sync(~0u, bad & 0xFFFFu)) break;
                    if (n > SPIN_LIMIT) __trap();
                }
#pragma unroll
                for (int k = 0; k < 4; k++) {
                    const int i = min(i0 + 64 * k, imax);
                    if (i < 224) {
                        const int isc = i >= 112, c4 = i - 112 * isc;
                        const float one = isc ? 1.f : 0.f;
                        const uint32_t a = sb + M_ST + (c4 >> 2) * 64 + (c4 & 1) * 32 + (c4 & 2) * 4 + (isc ? 0 : 4);
                        sts1(a, pack2(bf_hi(v[k].x) + one, bf_hi(v[k].y) + one));
                        sts1(a + 16, pack2(bf_hi(v[k].z) + one, bf_hi(v[k].w) + one));
                    } else {
                        sts4(sb + M_G + (i - 224) * 16, make_uint4(v[k].x & 0xFFFF0000u, v[k].y & 0xFFFF0000u, v[k].z & 0xFFFF0000u, v[k].w & 0xFFFF0000u));
                    }
                }
                warp_arrive(BAR(p2 ? B_MOD2 : B_MOD1));
            }
            if (warp == 9) {
#pragma unroll 1
                for (int kv = 0; kv < 2; kv++) {
                    mbar_wait(BAR(B_PUB + kv), 0);
                    wait_flags(g_flag + b * 128 + lane, target, (r >= 2 ? 6u : r == 1 ? 2u : 0u) << (8 * kv));
                    fence_async_global();
                    const uint32_t dst = sb + OFF_Y + (kv ? Y_VR : Y_K);
                    expect_e(BAR(B_KRFULL + kv), r >= 2 ? 28672 : r == 1 ? 14336 : 0);
                    if (r >= 2) bulk_e(dst, g_kv + (size_t)((b - 16) * 2 + kv) * 3584, 14336, BAR(B_KRFULL + kv));
                    if (r >= 1) bulk_e(dst + 14336, g_kv + (size_t)((b - 8) * 2 + kv) * 3584, 14336, BAR(B_KRFULL + kv));
                }
            } else if (warp == 11) {
                mbar_wait(BAR(B_VRFULL), 0);
                l2_prefetch_e((const char*)p.wg + (size_t)b * 12544, 12544);
                l2_prefetch_e((const char*)p.wu + (size_t)b * 12544, 12544);
#pragma unroll 1
                for (int k = 0; k < (r < 12 ? 2 : 1); k++) {
                    const int u = 28 * kh + r + 16 * k;
                    expect_e(BAR(B_XFULL + k), 7168);
                    tma3_e(sb + OFF_Y + 102400, &p.dn, 0, 32 * u, 14 * nq, BAR(B_XFULL + k));
                    mbar_wait(BAR(B_XFULL + k), 1);
                    asm volatile("{\n.reg .pred p;\nelect.sync _|p, 0xffffffff;\n@p cp.async.bulk.global.shared::cta.bulk_group [%0], [%1], 7168;\n"
                                 "cp.async.bulk.commit_group;\ncp.async.bulk.wait_group 0;\n}" ::"l"(g_wd + (size_t)(u * 4 + nq) * 1792), "r"(sb + OFF_Y + 102400) : "memory");
                    __syncwarp();
                }
                warp_arrive(BAR(B_WMFREE));
                fence_gpu();
                if (lane < 16) st_relaxed(g_flag + (8 * lane + j) * 128 + 96 + r, target);
            }
        }
        if (warp == 8 || warp == 11) {
            const int sec = warp == 11;
            if (sec) ring_loader<1>(p, sb, r, j, lane); else ring_loader<0>(p, sb, r, j, lane);
            mbar_wait(BAR(B_DONE), 0);
        } else if (warp == 9) {
#pragma unroll
            for (int ev = 0; ev < 4; ev++) { expect_e(BAR(B_GFULL + ev), ev < 2 ? HALF / 2 : 16384 + 4096); expect_e(BAR(B_XFULL + 2 + ev), ev < 2 ? HALF / 2 : HALF - 16384); }
            mbar_wait(BAR(B_PUB + 2), 0);
            const uint32_t* fp = g_flag + b * 128 + 32 + lane;
            const int par = (target - 1) & 1;
#pragma unroll 1
            for (int n = 0, ev = 0; ev < 4; n++) {
                if (ev == 1) { mbar_wait(BAR(B_WMFREE), 1); mbar_wait(BAR(B_PUB + 3), 0); }
                uint32_t ok = __ballot_sync(~0u, (int)(ld_relaxed(fp) - target) >= 0) >> (8 * ev);
                while ((ok & 0xFFu) == 0xFFu) {
                    asm volatile("fence.acquire.gpu;" ::: "memory");
                    fence_async_global();
                    const int tile = 2 * r + (ev & 1) + (ev >> 1) * par * 34;
                    const uint32_t dst = sb + (ev == 0 ? OFF_X : OFF_Y + (ev & 1) * HALF), first = ev < 2 ? HALF / 2 : 16384;
                    const char* src = (const char*)(g_ox + (size_t)((ev >> 1) * 34 + tile) * 14336);
                    if (ev >= 2) bulk_e(sb + OFF_X + X_STAT + (ev & 1) * 4096, g_st + tile * 512, 4096, BAR(B_GFULL + ev));
                    bulk_e(dst, src, first, BAR(B_GFULL + ev));
                    bulk_e(dst + first, src + first, HALF - first, BAR(B_XFULL + 2 + ev));
                    if (ev) PROFH(4 + ev);
                    ev++; ok >>= 8;
                }
                if (n > SPIN_LIMIT) __trap();
            }
            mbar_wait(BAR(B_XFULL + 5), 1);
#pragma unroll 1
            for (int hf = 0; hf < 2; hf++) {
                const int tile = (par ^ 1) * 34 + 2 * r + hf;
                uint4* xz = (uint4*)(g_x1 + (size_t)tile * 14336 + j * 1792) + lane;
#pragma unroll
                for (int i = 0; i < 14; i++) xz[i * 32] = make_uint4(0, 0, 0, 0);
                ((uint4*)(g_st + (tile * 8 + j) * 64))[lane] = make_uint4(0, 0, 0, 0);
            }
#pragma unroll 1
            for (int ps = 0; ps < 3; ps++) {
                mbar_wait(BAR(B_PUB + 6 + ps), 0);
                wait_flags(g_flag + b * 128 + 64 + lane, target, (0x55u << kh) << (8 * ps));
                warp_arrive(BAR(B_HRDY + ps));
                PROFH(9 + ps);
            }
        } else {
#pragma unroll 1
            for (int k = 0; k < 9; k++) {
                uint32_t* fp = k < 2 ? g_flag + (b + 8 * lane) * 128 + k * 8 + lane : g_flag + (8 * r + lane) * 128 + 16 + k * 8 + j;
                mbar_wait(BAR(B_PUB + k), 0);
                if (k != 4 && k != 5) fence_gpu();
                if (k < 2 ? (lane == 1 || lane == 2) : lane < 8) st_relaxed(fp, target);
                if (k >= 3 && k <= 5) PROFH(k - 3);
            }
        }
    }
}

typedef CUresult (*EncodeFn)(CUtensorMap*, CUtensorMapDataType, cuuint32_t, void*, const cuuint64_t*, const cuuint64_t*, const cuuint32_t*,
                             const cuuint32_t*, CUtensorMapInterleave, CUtensorMapSwizzle, CUtensorMapL2promotion, CUtensorMapFloatOOBfill);

static void make_map(EncodeFn fn, CUtensorMap* m, const void* ptr, uint64_t d0, uint64_t d1, uint64_t d2, uint64_t s1, uint64_t s2,
                     uint32_t b0, uint32_t b1, uint32_t b2, CUtensorMapSwizzle sw) {
    cuuint64_t dims[3] = {d0, d1, d2}, strides[2] = {s1, s2};
    cuuint32_t box[3] = {b0, b1, b2}, es[3] = {1, 1, 1};
    CUresult rc = fn(m, CU_TENSOR_MAP_DATA_TYPE_BFLOAT16, 3, (void*)ptr, dims, strides, box, es, CU_TENSOR_MAP_INTERLEAVE_NONE, sw,
                     CU_TENSOR_MAP_L2_PROMOTION_L2_128B, CU_TENSOR_MAP_FLOAT_OOB_FILL_NONE);
    (void)rc;
}

extern "C" void kernel_launch(void* const* d_in, const int* in_sizes, int n_in, void* d_out, int out_size) {
    (void)in_sizes; (void)n_in; (void)out_size;
    static EncodeFn fn = nullptr;
    if (!fn) {
        cudaDriverEntryPointQueryResult st;
        cudaGetDriverEntryPoint("cuTensorMapEncodeTiled", (void**)&fn, cudaEnableDefault, &st);
        cudaFuncSetAttribute(fused_block_kernel, cudaFuncAttributeMaxDynamicSharedMemorySize, SMEM_BYTES);
    }
    Params p;
    p.x = (const bf16*)d_in[0];
    const bf16* wqkv = (const bf16*)d_in[1];
    p.wqkv = wqkv;
    p.wop = (const bf16*)d_in[2];
    p.wg = (const bf16*)d_in[4];
    p.wu = (const bf16*)d_in[5];
    p.wd = (const bf16*)d_in[6];
    p.c = (const bf16*)d_in[7];
    p.wmod = (const bf16*)d_in[8];
    p.out = (bf16*)d_out;
    p.zero = 0;
    make_map(fn, &p.wm, p.wmod, 2688, 448, 1, 5376, 5376 * 448, 16, 224, 1, CU_TENSOR_MAP_SWIZZLE_NONE);
    make_map(fn, &p.xm, p.x, 448, 2048, 1, 896, 896 * 2048, 64, 128, 1, CU_TENSOR_MAP_SWIZZLE_128B);
    make_map(fn, &p.qkv, wqkv, 1344, 448, 1, 2688, 2688 * 448, 64, 224, 1, CU_TENSOR_MAP_SWIZZLE_128B);
    make_map(fn, &p.wo, p.wop, 448, 448, 1, 896, 896 * 448, 64, 224, 1, CU_TENSOR_MAP_SWIZZLE_128B);
    make_map(fn, &p.ga, p.wg, 64, 448, 28, 3584, 128, 64, 32, 2, CU_TENSOR_MAP_SWIZZLE_128B);
    make_map(fn, &p.ua, p.wu, 64, 448, 28, 3584, 128, 64, 32, 2, CU_TENSOR_MAP_SWIZZLE_128B);
    make_map(fn, &p.gb, p.wg, 64, 448, 28, 3584, 128, 64, 64, 1, CU_TENSOR_MAP_SWIZZLE_128B);
    make_map(fn, &p.ub, p.wu, 64, 448, 28, 3584, 128, 64, 64, 1, CU_TENSOR_MAP_SWIZZLE_128B);
    make_map(fn, &p.gc, p.wg, 32, 448, 56, 3584, 64, 32, 64, 1, CU_TENSOR_MAP_SWIZZLE_64B);
    make_map(fn, &p.uc, p.wu, 32, 448, 56, 3584, 64, 32, 64, 1, CU_TENSOR_MAP_SWIZZLE_64B);
    make_map(fn, &p.dn, p.wd, 8, 1792, 56, 896, 16, 8, 32, 14, CU_TENSOR_MAP_SWIZZLE_NONE);
    fused_block_kernel<<<GRID, 384, SMEM_BYTES>>>(p);
}
```

```cpp
#include <cuda_runtime.h>
#include <cuda_bf16.h>
#include <cuda.h>
#include <stdint.h>

typedef __nv_bfloat16 bf16;

template<uint64_t CB> __device__ __forceinline__ void wgmma_rs_56(float* d, uint32_t a0, uint32_t a1, uint32_t a2, uint32_t a3, uint32_t db, int sd) {
  asm volatile("{\n.reg .pred p;\n.reg .b64 b;\nsetp.ne.b32 p, %33, 0;\nmov.b64 b, {%32, %34};\n"
    "wgmma.mma_async.sync.aligned.m64n56k16.f32.bf16.bf16 {%0,%1,%2,%3,%4,%5,%6,%7,%8,%9,%10,%11,%12,%13,%14,%15,%16,%17,%18,%19,%20,%21,%22,%23,%24,%25,%26,%27}, {%28,%29,%30,%31}, b, p, 1, 1, 1;\n}\n"
    : "+f"(d[0]),"+f"(d[1]),"+f"(d[2]),"+f"(d[3]),"+f"(d[4]),"+f"(d[5]),"+f"(d[6]),"+f"(d[7]),"+f"(d[8]),"+f"(d[9]),"+f"(d[10]),"+f"(d[11]),"+f"(d[12]),"+f"(d[13]),"+f"(d[14]),"+f"(d[15]),"+f"(d[16]),"+f"(d[17]),"+f"(d[18]),"+f"(d[19]),"+f"(d[20]),"+f"(d[21]),"+f"(d[22]),"+f"(d[23]),"+f"(d[24]),"+f"(d[25]),"+f"(d[26]),"+f"(d[27])
    : "r"(a0), "r"(a1), "r"(a2), "r"(a3), "r"(db), "r"(sd), "n"((uint32_t)(CB >> 32)));
}
template<uint64_t CA, uint64_t CB> __device__ __forceinline__ void wgmma_ss_56(float* d, uint32_t da, uint32_t db, int sd) {
  asm volatile("{\n.reg .pred p;\n.reg .b64 a, b;\nsetp.ne.b32 p, %30, 0;\nmov.b64 a, {%28, %31};\nmov.b64 b, {%29, %32};\n"
    "wgmma.mma_async.sync.aligned.m64n56k16.f32.bf16.bf16 {%0,%1,%2,%3,%4,%5,%6,%7,%8,%9,%10,%11,%12,%13,%14,%15,%16,%17,%18,%19,%20,%21,%22,%23,%24,%25,%26,%27}, a, b, p, 1, 1, 0, 1;\n}\n"
    : "+f"(d[0]),"+f"(d[1]),"+f"(d[2]),"+f"(d[3]),"+f"(d[4]),"+f"(d[5]),"+f"(d[6]),"+f"(d[7]),"+f"(d[8]),"+f"(d[9]),"+f"(d[10]),"+f"(d[11]),"+f"(d[12]),"+f"(d[13]),"+f"(d[14]),"+f"(d[15]),"+f"(d[16]),"+f"(d[17]),"+f"(d[18]),"+f"(d[19]),"+f"(d[20]),"+f"(d[21]),"+f"(d[22]),"+f"(d[23]),"+f"(d[24]),"+f"(d[25]),"+f"(d[26]),"+f"(d[27])
    : "r"(da), "r"(db), "r"(sd), "n"((uint32_t)(CA >> 32)), "n"((uint32_t)(CB >> 32)));
}
template<uint64_t CB> __device__ __forceinline__ void wgmma_rs_256(float* d, uint32_t a0, uint32_t a1, uint32_t a2, uint32_t a3, uint32_t db, int sd) {
  asm volatile("{\n.reg .pred p;\n.reg .b64 b;\nsetp.ne.b32 p, %133, 0;\nmov.b64 b, {%132, %134};\n"
    "wgmma.mma_async.sync.aligned.m64n256k16.f32.bf16.bf16 {%0,%1,%2,%3,%4,%5,%6,%7,%8,%9,%10,%11,%12,%13,%14,%15,%16,%17,%18,%19,%20,%21,%22,%23,%24,%25,%26,%27,%28,%29,%30,%31,%32,%33,%34,%35,%36,%37,%38,%39,%40,%41,%42,%43,%44,%45,%46,%47,%48,%49,%50,%51,%52,%53,%54,%55,%56,%57,%58,%59,%60,%61,%62,%63,%64,%65,%66,%67,%68,%69,%70,%71,%72,%73,%74,%75,%76,%77,%78,%79,%80,%81,%82,%83,%84,%85,%86,%87,%88,%89,%90,%91,%92,%93,%94,%95,%96,%97,%98,%99,%100,%101,%102,%103,%104,%105,%106,%107,%108,%109,%110,%111,%112,%113,%114,%115,%116,%117,%118,%119,%120,%121,%122,%123,%124,%125,%126,%127}, {%128,%129,%130,%131}, b, p, 1, 1, 1;\n}\n"
    : "+f"(d[0]),"+f"(d[1]),"+f"(d[2]),"+f"(d[3]),"+f"(d[4]),"+f"(d[5]),"+f"(d[6]),"+f"(d[7]),"+f"(d[8]),"+f"(d[9]),"+f"(d[10]),"+f"(d[11]),"+f"(d[12]),"+f"(d[13]),"+f"(d[14]),"+f"(d[15]),"+f"(d[16]),"+f"(d[17]),"+f"(d[18]),"+f"(d[19]),"+f"(d[20]),"+f"(d[21]),"+f"(d[22]),"+f"(d[23]),"+f"(d[24]),"+f"(d[25]),"+f"(d[26]),"+f"(d[27]),"+f"(d[28]),"+f"(d[29]),"+f"(d[30]),"+f"(d[31]),"+f"(d[32]),"+f"(d[33]),"+f"(d[34]),"+f"(d[35]),"+f"(d[36]),"+f"(d[37]),"+f"(d[38]),"+f"(d[39]),"+f"(d[40]),"+f"(d[41]),"+f"(d[42]),"+f"(d[43]),"+f"(d[44]),"+f"(d[45]),"+f"(d[46]),"+f"(d[47]),"+f"(d[48]),"+f"(d[49]),"+f"(d[50]),"+f"(d[51]),"+f"(d[52]),"+f"(d[53]),"+f"(d[54]),"+f"(d[55]),"+f"(d[56]),"+f"(d[57]),"+f"(d[58]),"+f"(d[59]),"+f"(d[60]),"+f"(d[61]),"+f"(d[62]),"+f"(d[63]),"+f"(d[64]),"+f"(d[65]),"+f"(d[66]),"+f"(d[67]),"+f"(d[68]),"+f"(d[69]),"+f"(d[70]),"+f"(d[71]),"+f"(d[72]),"+f"(d[73]),"+f"(d[74]),"+f"(d[75]),"+f"(d[76]),"+f"(d[77]),"+f"(d[78]),"+f"(d[79]),"+f"(d[80]),"+f"(d[81]),"+f"(d[82]),"+f"(d[83]),"+f"(d[84]),"+f"(d[85]),"+f"(d[86]),"+f"(d[87]),"+f"(d[88]),"+f"(d[89]),"+f"(d[90]),"+f"(d[91]),"+f"(d[92]),"+f"(d[93]),"+f"(d[94]),"+f"(d[95]),"+f"(d[96]),"+f"(d[97]),"+f"(d[98]),"+f"(d[99]),"+f"(d[100]),"+f"(d[101]),"+f"(d[102]),"+f"(d[103]),"+f"(d[104]),"+f"(d[105]),"+f"(d[106]),"+f"(d[107]),"+f"(d[108]),"+f"(d[109]),"+f"(d[110]),"+f"(d[111]),"+f"(d[112]),"+f"(d[113]),"+f"(d[114]),"+f"(d[115]),"+f"(d[116]),"+f"(d[117]),"+f"(d[118]),"+f"(d[119]),"+f"(d[120]),"+f"(d[121]),"+f"(d[122]),"+f"(d[123]),"+f"(d[124]),"+f"(d[125]),"+f"(d[126]),"+f"(d[127])
    : "r"(a0), "r"(a1), "r"(a2), "r"(a3), "r"(db), "r"(sd), "n"((uint32_t)(CB >> 32)));
}
template<uint64_t CA, uint64_t CB> __device__ __forceinline__ void wgmma_ss_128(float* d, uint32_t da, uint32_t db, int sd) {
  asm volatile("{\n.reg .pred p;\n.reg .b64 a, b;\nsetp.ne.b32 p, %66, 0;\nmov.b64 a, {%64, %67};\nmov.b64 b, {%65, %68};\n"
    "wgmma.mma_async.sync.aligned.m64n128k16.f32.bf16.bf16 {%0,%1,%2,%3,%4,%5,%6,%7,%8,%9,%10,%11,%12,%13,%14,%15,%16,%17,%18,%19,%20,%21,%22,%23,%24,%25,%26,%27,%28,%29,%30,%31,%32,%33,%34,%35,%36,%37,%38,%39,%40,%41,%42,%43,%44,%45,%46,%47,%48,%49,%50,%51,%52,%53,%54,%55,%56,%57,%58,%59,%60,%61,%62,%63}, a, b, p, 1, 1, 0, 1;\n}\n"
    : "+f"(d[0]),"+f"(d[1]),"+f"(d[2]),"+f"(d[3]),"+f"(d[4]),"+f"(d[5]),"+f"(d[6]),"+f"(d[7]),"+f"(d[8]),"+f"(d[9]),"+f"(d[10]),"+f"(d[11]),"+f"(d[12]),"+f"(d[13]),"+f"(d[14]),"+f"(d[15]),"+f"(d[16]),"+f"(d[17]),"+f"(d[18]),"+f"(d[19]),"+f"(d[20]),"+f"(d[21]),"+f"(d[22]),"+f"(d[23]),"+f"(d[24]),"+f"(d[25]),"+f"(d[26]),"+f"(d[27]),"+f"(d[28]),"+f"(d[29]),"+f"(d[30]),"+f"(d[31]),"+f"(d[32]),"+f"(d[33]),"+f"(d[34]),"+f"(d[35]),"+f"(d[36]),"+f"(d[37]),"+f"(d[38]),"+f"(d[39]),"+f"(d[40]),"+f"(d[41]),"+f"(d[42]),"+f"(d[43]),"+f"(d[44]),"+f"(d[45]),"+f"(d[46]),"+f"(d[47]),"+f"(d[48]),"+f"(d[49]),"+f"(d[50]),"+f"(d[51]),"+f"(d[52]),"+f"(d[53]),"+f"(d[54]),"+f"(d[55]),"+f"(d[56]),"+f"(d[57]),"+f"(d[58]),"+f"(d[59]),"+f"(d[60]),"+f"(d[61]),"+f"(d[62]),"+f"(d[63])
    : "r"(da), "r"(db), "r"(sd), "n"((uint32_t)(CA >> 32)), "n"((uint32_t)(CB >> 32)));
}
template<uint64_t CA, uint64_t CB> __device__ __forceinline__ void wgmma_ss_64(float* d, uint32_t da, uint32_t db, int sd) {
  asm volatile("{\n.reg .pred p;\n.reg .b64 a, b;\nsetp.ne.b32 p, %34, 0;\nmov.b64 a, {%32, %35};\nmov.b64 b, {%33, %36};\n"
    "wgmma.mma_async.sync.aligned.m64n64k16.f32.bf16.bf16 {%0,%1,%2,%3,%4,%5,%6,%7,%8,%9,%10,%11,%12,%13,%14,%15,%16,%17,%18,%19,%20,%21,%22,%23,%24,%25,%26,%27,%28,%29,%30,%31}, a, b, p, 1, 1, 0, 1;\n}\n"
    : "+f"(d[0]),"+f"(d[1]),"+f"(d[2]),"+f"(d[3]),"+f"(d[4]),"+f"(d[5]),"+f"(d[6]),"+f"(d[7]),"+f"(d[8]),"+f"(d[9]),"+f"(d[10]),"+f"(d[11]),"+f"(d[12]),"+f"(d[13]),"+f"(d[14]),"+f"(d[15]),"+f"(d[16]),"+f"(d[17]),"+f"(d[18]),"+f"(d[19]),"+f"(d[20]),"+f"(d[21]),"+f"(d[22]),"+f"(d[23]),"+f"(d[24]),"+f"(d[25]),"+f"(d[26]),"+f"(d[27]),"+f"(d[28]),"+f"(d[29]),"+f"(d[30]),"+f"(d[31])
    : "r"(da), "r"(db), "r"(sd), "n"((uint32_t)(CA >> 32)), "n"((uint32_t)(CB >> 32)));
}
template<uint64_t CA, uint64_t CB> __device__ __forceinline__ void wgmma_ss_112(float* d, uint32_t da, uint32_t db, int sd) {
  asm volatile("{\n.reg .pred p;\n.reg .b64 a, b;\nsetp.ne.b32 p, %58, 0;\nmov.b64 a, {%56, %59};\nmov.b64 b, {%57, %60};\n"
    "wgmma.mma_async.sync.aligned.m64n112k16.f32.bf16.bf16 {%0,%1,%2,%3,%4,%5,%6,%7,%8,%9,%10,%11,%12,%13,%14,%15,%16,%17,%18,%19,%20,%21,%22,%23,%24,%25,%26,%27,%28,%29,%30,%31,%32,%33,%34,%35,%36,%37,%38,%39,%40,%41,%42,%43,%44,%45,%46,%47,%48,%49,%50,%51,%52,%53,%54,%55}, a, b, p, 1, 1, 0, 1;\n}\n"
    : "+f"(d[0]),"+f"(d[1]),"+f"(d[2]),"+f"(d[3]),"+f"(d[4]),"+f"(d[5]),"+f"(d[6]),"+f"(d[7]),"+f"(d[8]),"+f"(d[9]),"+f"(d[10]),"+f"(d[11]),"+f"(d[12]),"+f"(d[13]),"+f"(d[14]),"+f"(d[15]),"+f"(d[16]),"+f"(d[17]),"+f"(d[18]),"+f"(d[19]),"+f"(d[20]),"+f"(d[21]),"+f"(d[22]),"+f"(d[23]),"+f"(d[24]),"+f"(d[25]),"+f"(d[26]),"+f"(d[27]),"+f"(d[28]),"+f"(d[29]),"+f"(d[30]),"+f"(d[31]),"+f"(d[32]),"+f"(d[33]),"+f"(d[34]),"+f"(d[35]),"+f"(d[36]),"+f"(d[37]),"+f"(d[38]),"+f"(d[39]),"+f"(d[40]),"+f"(d[41]),"+f"(d[42]),"+f"(d[43]),"+f"(d[44]),"+f"(d[45]),"+f"(d[46]),"+f"(d[47]),"+f"(d[48]),"+f"(d[49]),"+f"(d[50]),"+f"(d[51]),"+f"(d[52]),"+f"(d[53]),"+f"(d[54]),"+f"(d[55])
    : "r"(da), "r"(db), "r"(sd), "n"((uint32_t)(CA >> 32)), "n"((uint32_t)(CB >> 32)));
}
template<uint64_t CB> __device__ __forceinline__ void wgmma_rs_112(float* d, uint32_t a0, uint32_t a1, uint32_t a2, uint32_t a3, uint32_t db, int sd) {
  asm volatile("{\n.reg .pred p;\n.reg .b64 b;\nsetp.ne.b32 p, %61, 0;\nmov.b64 b, {%60, %62};\n"
    "wgmma.mma_async.sync.aligned.m64n112k16.f32.bf16.bf16 {%0,%1,%2,%3,%4,%5,%6,%7,%8,%9,%10,%11,%12,%13,%14,%15,%16,%17,%18,%19,%20,%21,%22,%23,%24,%25,%26,%27,%28,%29,%30,%31,%32,%33,%34,%35,%36,%37,%38,%39,%40,%41,%42,%43,%44,%45,%46,%47,%48,%49,%50,%51,%52,%53,%54,%55}, {%56,%57,%58,%59}, b, p, 1, 1, 1;\n}\n"
    : "+f"(d[0]),"+f"(d[1]),"+f"(d[2]),"+f"(d[3]),"+f"(d[4]),"+f"(d[5]),"+f"(d[6]),"+f"(d[7]),"+f"(d[8]),"+f"(d[9]),"+f"(d[10]),"+f"(d[11]),"+f"(d[12]),"+f"(d[13]),"+f"(d[14]),"+f"(d[15]),"+f"(d[16]),"+f"(d[17]),"+f"(d[18]),"+f"(d[19]),"+f"(d[20]),"+f"(d[21]),"+f"(d[22]),"+f"(d[23]),"+f"(d[24]),"+f"(d[25]),"+f"(d[26]),"+f"(d[27]),"+f"(d[28]),"+f"(d[29]),"+f"(d[30]),"+f"(d[31]),"+f"(d[32]),"+f"(d[33]),"+f"(d[34]),"+f"(d[35]),"+f"(d[36]),"+f"(d[37]),"+f"(d[38]),"+f"(d[39]),"+f"(d[40]),"+f"(d[41]),"+f"(d[42]),"+f"(d[43]),"+f"(d[44]),"+f"(d[45]),"+f"(d[46]),"+f"(d[47]),"+f"(d[48]),"+f"(d[49]),"+f"(d[50]),"+f"(d[51]),"+f"(d[52]),"+f"(d[53]),"+f"(d[54]),"+f"(d[55])
    : "r"(a0), "r"(a1), "r"(a2), "r"(a3), "r"(db), "r"(sd), "n"((uint32_t)(CB >> 32)));
}

constexpr int DM = 448;
constexpr int NCTA = 128;
#define MAPPING 1
#define GRID 132
#define PINGPONG 0
#define WIN 6
#define WIN_END 25
#define UNR_G2 21
#define UNR_B 7
#define UNR_C 7
constexpr int kG2 = UNR_G2, kB = UNR_B, kC = UNR_C;
#define PACE 1
#define PACE_END 6
#define MAP_S 4
constexpr int SPIN_LIMIT = 1 << 22;

constexpr uint32_t OFF_X = 0, OFF_Y = 114688, OFF_MISC = 229376, SMEM_BYTES = 232448;
constexpr uint32_t Y_VR = 0, Y_K = 28672, Y_KOWN = 57344, Y_VOWN = 71680, Y_Q = 86016;
constexpr uint32_t HALF = 57344;
constexpr uint32_t M_BAR = OFF_MISC;
constexpr uint32_t M_ST = OFF_MISC + 512;
constexpr uint32_t M_G = OFF_MISC + 2304;
constexpr uint32_t M_EPOCH = OFF_MISC + 3040;
enum { B_XFULL = 0, B_FULLK = 7, B_FULLV = 8, B_FULLQ, B_KRFULL, B_VRFULL, B_WOFULL, B_XCH, B_FULL = 16, B_MOD1 = 28, B_MOD2, B_WMFULL,
       B_EMPTY = 32, B_XFREE = B_EMPTY + 12, B_GEMV, B_PEER,
       B_PUB = 47,
       B_WMFREE = 56, B_HRDY, B_GFULL = B_HRDY + 3, B_DONE = 31 };
constexpr uint32_t X_STAT = 49152;

__device__ uint32_t g_ticket;
__device__ __align__(128) uint32_t g_mod[8 * 6 * DM];
__device__ __align__(128) uint32_t g_flag[144 * 128];
constexpr int RB_WORDS = 262144, RB_KV = 0, RB_O = 57344, RB_X1 = 86016, RB_H2 = 143360, RB_ST = 258048;
__device__ __align__(128) uint32_t g_act[18 * RB_WORDS];
__device__ __align__(128) uint32_t g_wd[56 * 4 * 1792];
#define PROFH(id)
#define PROFH1(id)
#define PROFC(id)

struct alignas(64) Params {
    CUtensorMap wm, xm, qkv, wo, ga, ua, gb, ub, gc, uc, dn;
    const bf16 *x, *c, *wqkv, *wmod, *wg, *wu, *wd, *wop;
    bf16* out;
    uint32_t* actb;
    uint32_t zero;
};

__device__ __forceinline__ void mbar_init(uint32_t bar, int cnt) { asm volatile("mbarrier.init.shared::cta.b64 [%0], %1;" ::"r"(bar), "r"(cnt) : "memory"); }
__device__ __forceinline__ void mbar_expect_tx(uint32_t bar, uint32_t bytes) { asm volatile("mbarrier.arrive.expect_tx.shared::cta.b64 _, [%0], %1;" ::"r"(bar), "r"(bytes) : "memory"); }
__device__ __forceinline__ void mbar_arrive(uint32_t bar) { asm volatile("mbarrier.arrive.shared::cta.b64 _, [%0];" ::"r"(bar) : "memory"); }
__device__ __forceinline__ void mbar_wait(uint32_t bar, uint32_t parity) {
    uint32_t ok; int n = 0;
    do {
        asm volatile("{\n.reg .pred p;\nmbarrier.try_wait.parity.shared::cta.b64 p, [%1], %2;\nselp.u32 %0, 1, 0, p;\n}" : "=r"(ok) : "r"(bar), "r"(parity) : "memory");
        if (++n > SPIN_LIMIT) __trap();
    } while (!ok);
}
__device__ __forceinline__ void mbar_wait_c(uint32_t bar, uint32_t parity) {
    asm volatile("{\n.reg .pred p;\nWL:\nmbarrier.try_wait.parity.shared::cta.b64 p, [%0], %1;\n@!p bra WL;\n}" ::"r"(bar), "r"(parity) : "memory");
}
__device__ __forceinline__ void mbar_wait_cluster(uint32_t bar, uint32_t parity) {
    uint32_t ok; int n = 0;
    do {
        asm volatile("{\n.reg .pred p;\nmbarrier.try_wait.parity.acquire.cluster.shared::cta.b64 p, [%1], %2;\nselp.u32 %0, 1, 0, p;\n}" : "=r"(ok) : "r"(bar), "r"(parity) : "memory");
        if (++n > SPIN_LIMIT) __trap();
    } while (!ok);
}
__device__ __forceinline__ void warp_arrive(uint32_t bar) {
    __syncwarp();
    asm volatile("{\n.reg .pred p;\nelect.sync _|p, 0xffffffff;\n@p mbarrier.arrive.shared::cta.b64 _, [%0];\n}" ::"r"(bar) : "memory");
}
__device__ __forceinline__ int opaque(int v) { return __shfl_sync(~0u, v, 0); }
__device__ __forceinline__ int fresh_tid() { int v; asm volatile("mov.u32 %0, %%tid.x;" : "=r"(v)); return v; }
__device__ __forceinline__ void bar_sync(int id, int n) { asm volatile("bar.sync %0, %1;" ::"r"(id), "r"(n) : "memory"); }
__device__ __forceinline__ void bar_arrive(int id, int n) { asm volatile("bar.arrive %0, %1;" ::"r"(id), "r"(n) : "memory"); }
__device__ __forceinline__ void fence_async_smem() { asm volatile("fence.proxy.async.shared::cta;" ::: "memory"); }
__device__ __forceinline__ void fence_async_global() { asm volatile("fence.proxy.async.global;" ::: "memory"); }
__device__ __forceinline__ void fence_gpu() { asm volatile("fence.release.gpu;" ::: "memory"); }
__device__ __forceinline__ void tma3(uint32_t dst, const CUtensorMap* m, int c0, int c1, int c2, uint32_t bar) {
    asm volatile("cp.async.bulk.tensor.3d.shared::cluster.global.mbarrier::complete_tx::bytes [%0], [%1, {%3, %4, %5}], [%2];"
                 ::"r"(dst), "l"(m), "r"(bar), "r"(c0), "r"(c1), "r"(c2) : "memory");
}
__device__ __forceinline__ void bulk_load(uint32_t dst, const void* src, uint32_t bytes, uint32_t bar) {
    asm volatile("cp.async.bulk.shared::cluster.global.mbarrier::complete_tx::bytes [%0], [%1], %2, [%3];" ::"r"(dst), "l"(src), "r"(bytes), "r"(bar) : "memory");
}
__device__ __forceinline__ void expect_e(uint32_t bar, uint32_t bytes) {
    asm volatile("{\n.reg .pred p;\nelect.sync _|p, 0xffffffff;\n@p mbarrier.arrive.expect_tx.shared::cta.b64 _, [%0], %1;\n}" ::"r"(bar), "r"(bytes) : "memory");
}
__device__ __forceinline__ void tma3_e(uint32_t dst, const CUtensorMap* m, int c0, int c1, int c2, uint32_t bar) {
    asm volatile("{\n.reg .pred p;\nelect.sync _|p, 0xffffffff;\n@p cp.async.bulk.tensor.3d.shared::cluster.global.mbarrier::complete_tx::bytes [%0], [%1, {%3, %4, %5}], [%2];\n}"
                 ::"r"(dst), "l"(m), "r"(bar), "r"(c0), "r"(c1), "r"(c2) : "memory");
}
__device__ __forceinline__ void bulk_e(uint32_t dst, const void* src, uint32_t bytes, uint32_t bar) {
    asm volatile("{\n.reg .pred p;\nelect.sync _|p, 0xffffffff;\n@p cp.async.bulk.shared::cluster.global.mbarrier::complete_tx::bytes [%0], [%1], %2, [%3];\n}"
                 ::"r"(dst), "l"(src), "r"(bytes), "r"(bar) : "memory");
}
__device__ __forceinline__ void init_e(uint32_t bar, int cnt) {
    asm volatile("{\n.reg .pred p;\nelect.sync _|p, 0xffffffff;\n@p mbarrier.init.shared::cta.b64 [%0], %1;\n}" ::"r"(bar), "r"(cnt) : "memory");
}
__device__ __forceinline__ void l2_prefetch_e(const void* src, uint32_t bytes) {
    asm volatile("{\n.reg .pred p;\nelect.sync _|p, 0xffffffff;\n@p cp.async.bulk.prefetch.L2.global [%0], %1;\n}" ::"l"(src), "r"(bytes) : "memory");
}
__device__ __forceinline__ uint32_t ld_relaxed(const uint32_t* p) { uint32_t v; asm volatile("ld.relaxed.gpu.global.u32 %0, [%1];" : "=r"(v) : "l"(p) : "memory"); return v; }
__device__ __forceinline__ void st_relaxed(uint32_t* p, uint32_t v) { asm volatile("st.relaxed.gpu.global.u32 [%0], %1;" ::"l"(p), "r"(v) : "memory"); }
__device__ __forceinline__ uint4 ld_relaxed4(const uint4* p) { uint4 v; asm volatile("ld.relaxed.gpu.global.v4.u32 {%0,%1,%2,%3}, [%4];" : "=r"(v.x), "=r"(v.y), "=r"(v.z), "=r"(v.w) : "l"(p) : "memory"); return v; }
__device__ __forceinline__ void st_relaxed4(uint4* p, uint4 v) { asm volatile("st.relaxed.gpu.global.v4.u32 [%0], {%1,%2,%3,%4};" ::"l"(p), "r"(v.x), "r"(v.y), "r"(v.z), "r"(v.w) : "memory"); }
__device__ __forceinline__ uint4 ldg_nc4(const void* p) { uint4 v; asm volatile("ld.global.nc.L1::no_allocate.v4.u32 {%0,%1,%2,%3}, [%4];" : "=r"(v.x), "=r"(v.y), "=r"(v.z), "=r"(v.w) : "l"(p)); return v; }
__device__ __forceinline__ uint32_t ldg_nc(const void* p) { uint32_t v; asm volatile("ld.global.nc.u32 %0, [%1];" : "=r"(v) : "l"(p)); return v; }
__device__ __forceinline__ uint32_t ld_acquire(const uint32_t* p) { uint32_t v; asm volatile("ld.acquire.gpu.global.u32 %0, [%1];" : "=r"(v) : "l"(p) : "memory"); return v; }
__device__ __forceinline__ uint4 lds4(uint32_t a) { uint4 v; asm volatile("ld.shared.v4.u32 {%0,%1,%2,%3}, [%4];" : "=r"(v.x), "=r"(v.y), "=r"(v.z), "=r"(v.w) : "r"(a) : "memory"); return v; }
__device__ __forceinline__ float2 lds2f(uint32_t a) { float2 v; asm volatile("ld.shared.v2.f32 {%0,%1}, [%2];" : "=f"(v.x), "=f"(v.y) : "r"(a) : "memory"); return v; }
__device__ __forceinline__ uint32_t lds1(uint32_t a) { uint32_t v; asm volatile("ld.shared.u32 %0, [%1];" : "=r"(v) : "r"(a) : "memory"); return v; }
__device__ __forceinline__ void sts4(uint32_t a, uint4 v) { asm volatile("st.shared.v4.u32 [%0], {%1,%2,%3,%4};" ::"r"(a), "r"(v.x), "r"(v.y), "r"(v.z), "r"(v.w) : "memory"); }
__device__ __forceinline__ void sts2(uint32_t a, uint32_t x, uint32_t y) { asm volatile("st.shared.v2.u32 [%0], {%1,%2};" ::"r"(a), "r"(x), "r"(y) : "memory"); }
__device__ __forceinline__ void sts1(uint32_t a, uint32_t v) { asm volatile("st.shared.u32 [%0], %1;" ::"r"(a), "r"(v) : "memory"); }
__device__ __forceinline__ void stsm4(uint32_t a, uint32_t r0, uint32_t r1, uint32_t r2, uint32_t r3) {
    asm volatile("stmatrix.sync.aligned.m8n8.x4.shared.b16 [%0], {%1,%2,%3,%4};" ::"r"(a), "r"(r0), "r"(r1), "r"(r2), "r"(r3));
}
__device__ __forceinline__ uint32_t pack2(float lo, float hi) { uint32_t r; asm("cvt.rn.bf16x2.f32 %0, %1, %2;" : "=r"(r) : "f"(hi), "f"(lo)); return r; }
__device__ __forceinline__ uint32_t pack2_relu(float lo, float hi) { uint32_t r; asm("cvt.rn.relu.bf16x2.f32 %0, %1, %2;" : "=r"(r) : "f"(hi), "f"(lo)); return r; }
__device__ __forceinline__ uint32_t hfma2(uint32_t a, uint32_t b, uint32_t c) { uint32_t r; asm("fma.rn.bf16x2 %0, %1, %2, %3;" : "=r"(r) : "r"(a), "r"(b), "r"(c)); return r; }
__device__ __forceinline__ uint32_t hmul2(uint32_t a, uint32_t b) { uint32_t r; asm("mul.rn.bf16x2 %0, %1, %2;" : "=r"(r) : "r"(a), "r"(b)); return r; }
__device__ __forceinline__ float bf_lo(uint32_t v) { return __uint_as_float(v << 16); }
__device__ __forceinline__ float bf_hi(uint32_t v) { return __uint_as_float(v & 0xFFFF0000u); }
__device__ __forceinline__ float bf_round(float v) { return bf_lo(pack2(v, 0.f)); }
__device__ __forceinline__ float ex2(float x) { float r; asm("ex2.approx.ftz.f32 %0, %1;" : "=f"(r) : "f"(x)); return r; }
__device__ __forceinline__ void mma16816(float* d, uint32_t a0, uint32_t a1, uint32_t a2, uint32_t a3, uint32_t b0, uint32_t b1) {
    asm("mma.sync.aligned.m16n8k16.row.col.f32.bf16.bf16.f32 {%0,%1,%2,%3}, {%4,%5,%6,%7}, {%8,%9}, {%0,%1,%2,%3};"
        : "+f"(d[0]), "+f"(d[1]), "+f"(d[2]), "+f"(d[3]) : "r"(a0), "r"(a1), "r"(a2), "r"(a3), "r"(b0), "r"(b1));
}
__device__ __forceinline__ void mma16816_first(float* d, uint32_t a0, uint32_t a1, uint32_t a2, uint32_t a3, uint32_t b0, uint32_t b1) {
    asm volatile("mma.sync.aligned.m16n8k16.row.col.f32.bf16.bf16.f32 {%0,%1,%2,%3}, {%4,%5,%6,%7}, {%8,%9}, {%10,%10,%10,%10};"
        : "=f"(d[0]), "=f"(d[1]), "=f"(d[2]), "=f"(d[3]) : "r"(a0), "r"(a1), "r"(a2), "r"(a3), "r"(b0), "r"(b1), "f"(0.f));
}
__device__ __forceinline__ void mma16816_v(float* d, uint32_t a0, uint32_t a1, uint32_t a2, uint32_t a3, uint32_t b0, uint32_t b1) {
    asm volatile("mma.sync.aligned.m16n8k16.row.col.f32.bf16.bf16.f32 {%0,%1,%2,%3}, {%4,%5,%6,%7}, {%8,%9}, {%0,%1,%2,%3};"
        : "+f"(d[0]), "+f"(d[1]), "+f"(d[2]), "+f"(d[3]) : "r"(a0), "r"(a1), "r"(a2), "r"(a3), "r"(b0), "r"(b1));
}
__device__ __forceinline__ void mma1688(float* d, uint32_t a0, uint32_t a1, uint32_t b0) {
    asm("mma.sync.aligned.m16n8k8.row.col.f32.bf16.bf16.f32 {%0,%1,%2,%3}, {%4,%5}, {%6}, {%0,%1,%2,%3};"
        : "+f"(d[0]), "+f"(d[1]), "+f"(d[2]), "+f"(d[3]) : "r"(a0), "r"(a1), "r"(b0));
}
__device__ __forceinline__ void ldsm4(uint32_t a, uint32_t* r) {
    asm volatile("ldmatrix.sync.aligned.m8n8.x4.shared.b16 {%0,%1,%2,%3}, [%4];" : "=r"(r[0]), "=r"(r[1]), "=r"(r[2]), "=r"(r[3]) : "r"(a));
}
__device__ __forceinline__ void ldsm4t(uint32_t a, uint32_t* r) {
    asm volatile("ldmatrix.sync.aligned.m8n8.x4.trans.shared.b16 {%0,%1,%2,%3}, [%4];" : "=r"(r[0]), "=r"(r[1]), "=r"(r[2]), "=r"(r[3]) : "r"(a));
}
__device__ __forceinline__ float rcp(float x) { float r; asm("rcp.approx.ftz.f32 %0, %1;" : "=f"(r) : "f"(x)); return r; }
__device__ __forceinline__ uint2 ld_relaxed2(const void* p) { uint2 v; asm volatile("ld.relaxed.gpu.global.v2.u32 {%0,%1}, [%2];" : "=r"(v.x), "=r"(v.y) : "l"(p) : "memory"); return v; }
__device__ __forceinline__ void st_relaxed2(void* p, uint32_t x, uint32_t y) { asm volatile("st.relaxed.gpu.global.v2.u32 [%0], {%1,%2};" ::"l"(p), "r"(max(x, 1u)), "r"(max(y, 1u)) : "memory"); }
__host__ __device__ constexpr uint64_t dconst(uint32_t lbo, uint32_t sbo, uint32_t swz) {
    return ((uint64_t)(lbo >> 4) << 16) | ((uint64_t)(sbo >> 4) << 32) | ((uint64_t)swz << 62);
}
__device__ __forceinline__ uint32_t mkdesc(uint32_t addr, uint64_t c) { return (uint32_t)c | ((addr & 0x3FFFF) >> 4); }
#define WG_FENCE() asm volatile("wgmma.fence.sync.aligned;" ::: "memory")
#define WG_COMMIT() asm volatile("wgmma.commit_group.sync.aligned;" ::: "memory")
#define WG_WAIT(n) asm volatile("wgmma.wait_group.sync.aligned %0;" ::"n"(n) : "memory")
template <int N> __device__ __forceinline__ void reg_fence(float* d) {
#pragma unroll
    for (int i = 0; i < N; i++) asm volatile("" : "+f"(d[i])::"memory");
}
template <int N> __device__ __forceinline__ void reg_def(float* d) {
#pragma unroll
    for (int i = 0; i < N; i++) asm volatile("" : "=f"(d[i]));
}
template <int N> __device__ __forceinline__ void reg_def(uint32_t* d) {
#pragma unroll
    for (int i = 0; i < N; i++) asm volatile("" : "=r"(d[i]));
}
__device__ __forceinline__ bool is_unset(uint4 v) { return min(min(v.x, v.y), min(v.z, v.w)) == 0u; }
__device__ __forceinline__ uint4 nz4(uint32_t a, uint32_t b, uint32_t c, uint32_t d) { return make_uint4(max(a, 1u), max(b, 1u), max(c, 1u), max(d, 1u)); }
__device__ __forceinline__ void wait_flags(const uint32_t* p, uint32_t target, uint32_t mask) {
    int n = 0;
    while (~__ballot_sync(~0u, (int)(ld_relaxed(p) - target) >= 0) & mask) { if (++n > SPIN_LIMIT) __trap(); }
    asm volatile("fence.acquire.gpu;" ::: "memory");
}
__device__ __forceinline__ float silu_bf(uint32_t cbits) {
    const float c = __uint_as_float(cbits << 16);
    return bf_round(__fdividef(c, 1.f + fminf(ex2(-1.4426950408889634f * c), 1e30f)));
}
__device__ __forceinline__ void gemv_part(uint32_t wmbuf, int npanel, int wp, int lane) {
    const uint32_t wa = wmbuf + wp * 512 + (8 * (lane >> 4) + (lane & 7)) * 32 + ((lane >> 3) & 1) * 16;
    uint2 B[4];
#pragma unroll
    for (int i = 0; i < 4; i++) { const float2 v = lds2f(wmbuf + 28672 + (wp + 8 * i) * 32 + (lane & 3) * 8); B[i] = make_uint2(__float_as_uint(v.x), __float_as_uint(v.y)); }
#pragma unroll 1
    for (int pn = 0; pn < npanel; pn++) {
        float d[4] = {};
        uint32_t A[16];
#pragma unroll
        for (int i = 0; i < 4; i++) ldsm4t(wa + pn * 14336 + (i < 3 || wp < 4 ? i : 0) * 4096, A + 4 * i);
#pragma unroll
        for (int i = 0; i < 4; i++) mma16816(d, A[4 * i], A[4 * i + 1], A[4 * i + 2], A[4 * i + 3], B[i].x, B[i].y);
        if ((lane & 3) == 0) {
            sts1(wmbuf + 29696 + (wp * 32 + pn * 16 + (lane >> 2)) * 4, __float_as_uint(d[0]));
            sts1(wmbuf + 29696 + (wp * 32 + pn * 16 + 8 + (lane >> 2)) * 4, __float_as_uint(d[2]));
        }
    }
}
__device__ __forceinline__ int pass_f(int fs, int ps) { return 224 * fs + ((fs & 1) ? (ps == 0 ? 96 : ps == 1 ? 32 : 0) : (ps == 0 ? 0 : ps == 1 ? 128 : 192)); }
__device__ __forceinline__ constexpr uint32_t slot_off(int l) { return (l < 3 || l > 6 ? l : l == 6 ? 3 : l + 1) * 16384; }
__device__ __forceinline__ void ln_coeffs(float mean, float msq, uint32_t& r2, uint32_t& n2) {
    const float rs = bf_round(rsqrtf(fmaxf(msq - mean * mean, 0.f) + 1e-5f));
    r2 = pack2(rs, rs);
    n2 = pack2(-mean * rs, -mean * rs);
}

#define LOADW bulk_e(dst, g_wd + (size_t)((f >> 5) * 4 + nq) * 1792, 7168, bar);
template <int sec> __device__ __forceinline__ void ring_loader(const Params& p, uint32_t sb_, int r_, int j_, int lane) {
    const uint32_t sb = opaque(sb_);
    const int r = opaque(r_), j = opaque(j_), nq = j >> 1, fs = 4 * (j & 1) + nq;
    const int fa = pass_f(fs, 0), fb = pass_f(fs, 1), fc = pass_f(fs, 2);
#define BAR(i) (sb + M_BAR + 8 * (i))
#define kh (j & 1)
            int sl = 0;
            mbar_wait(BAR(B_PUB + 2), 0);
            wait_flags(g_flag + (8 * r + j) * 128 + 96 + lane, lds1(sb + M_EPOCH) + 1, 0xFFFFu);
            fence_async_global();
#pragma unroll 1
            for (int s = 0; s < 28; s++) {
                if (s >= PACE && s < PACE_END) mbar_wait(BAR(B_FULL + s - PACE), 0);
                const int ps = s < 14 ? 0 : s < 21 ? 1 : 2;
                const uint32_t half = ps < 2 ? 8192 : 4096;
                mbar_wait(BAR(B_EMPTY + sl), (s >= 7 && s < 14) || s >= 21);
                expect_e(BAR(B_FULL + sl), half);
                tma3_e(sb + slot_off(sl) + sec * half, &p.ga + 2 * ps + sec, 0, ps ? 64 * sl : 32 * s, ps == 0 ? fa >> 6 : ps == 1 ? fb >> 6 : fc >> 5, BAR(B_FULL + sl));
                sl = sl == 6 ? 0 : sl + 1;
            }
            if (!sec) PROFH(3);
#pragma unroll 1
            for (int e = 0; e < 4; e++) {
                const uint32_t dst = sb + slot_off(e) + sec * 8192, bar = BAR(B_FULL + e);
                const int f = (e < 2 ? fa + 64 * e : e == 2 ? fb : fc) + 32 * sec;
                mbar_wait(BAR(B_EMPTY + e), 0);
                expect_e(bar, e == 3 && sec ? 0 : 7168);
                if (!(e == 3 && sec)) { LOADW }
            }
            sl = 4;
            int e = 4;
#pragma unroll 1
            for (int grp = 0; grp < 9; grp++) {
                const int ps = grp >= 6 ? 2 : grp >= 3 ? 1 : 0;
                int sidx = grp - 3 * ps;
                if (sec && sidx == 0) { mbar_wait(BAR(B_HRDY + ps), 0); fence_async_global(); }
                sidx += sidx >= nq;
                int f = pass_f(4 * kh + sidx, ps);
#pragma unroll 1
                for (int k = 4 >> ps; k > 0; k--, e++, f += 32) {
                    const uint32_t dst = sb + slot_off(sl), bar = BAR(B_FULL + sl);
                    mbar_wait(BAR(B_EMPTY + sl), e >= 12 && e < 24);
                    if (e < WIN_END && e >= WIN) mbar_wait(BAR(B_FULL + (sl >= WIN ? sl - WIN : sl + 12 - WIN)), e - WIN >= 12);
                    expect_e(bar, sec ? 8192 : 7168);
                    if (!sec) { LOADW }
                    else bulk_e(dst + 8192, p.actb + (size_t)r * RB_WORDS + RB_H2 + f * 64, 8192, bar);
                    sl = sl == 11 ? 0 : sl + 1;
                }
            }
            if (!sec) PROFH(4);
}

__global__ void __cluster_dims__(2, 1, 1) __launch_bounds__(384, 1) fused_block_kernel(const __grid_constant__ Params p) {
    extern __shared__ __align__(1024) unsigned char smem[];
    const uint32_t sb = (uint32_t)__cvta_generic_to_shared(smem);
    const int tid = threadIdx.x, lane = tid & 31, warp = __shfl_sync(~0u, tid >> 5, 0);
    const int m = blockIdx.x >> 1;
    int r, nq;
    {
        int g, i;
        if (m < MAP_S) { g = m < 4 ? 15 : 16; i = m & 3; }
        else if (m < MAP_S + 32) { g = (m - MAP_S) & 7; i = (m - MAP_S) >> 3; }
        else if (m < MAP_S + 60) { i = (m - MAP_S - 32) / 7; g = 8 + (m - MAP_S - 32) - 7 * i; }
        else { g = 16; i = m & 3; }
        r = g; nq = i;
    }
    const int j = opaque(2 * nq + (blockIdx.x & 1)), b = 8 * r + j, fs = 4 * kh + nq;
#define act (p.actb + (size_t)r * RB_WORDS)
    const uint32_t sc = r == 16;
    if (lane == 0 && warp < 9 && warp != 6 && warp != 7) {
        const int i0 = warp == 8 ? 0 : 8 + 8 * warp, cnt = warp == 0 || warp == 8 ? 1 : warp < 3 ? 2 : 8;
#pragma unroll
        for (int k = 0; k < 8; k++) if (i0 + k != B_WMFULL) mbar_init(BAR(i0 + k), cnt);
        asm volatile("fence.mbarrier_init.release.cluster;" ::: "memory");
        fence_async_smem();
    }

    if (warp < 8) {
        const int w = warp >> 2, wi = warp & 3;
#define COORDS const int t = fresh_tid() & 127, lane = t & 31, q = lane & 3, lr = lane >> 2, ra = 64 * w + 16 * wi + lr; \
        const uint32_t lx = (lane >> 4) ^ (lane & 7), mrow = (64 * w + 16 * wi + ((lane >> 3) & 1) * 8 + (lane & 7)) * 128; \
        (void)q; (void)lr; (void)ra; (void)lx; (void)mrow;
        const int sid = 2 * (j & 3) + w;
#define RUN(k) (!sc || sid == (k))
#define WAIT(i, par) mbar_wait_c(BAR(i), (par) | sc)
        constexpr uint64_t DB128 = dconst(4096, 1024, 1);
        bar_arrive(9, 384);
        bar_sync(0, 384);
        asm volatile("barrier.cluster.arrive.relaxed.aligned;" ::: "memory");
        asm volatile("setmaxnreg.inc.sync.aligned.u32 224;");
        PROFC(0);
        uint32_t xr[16];
        {
            COORDS
            uint32_t h[112];
            if (RUN(0)) {
                float ds[4] = {}, da[2][4] = {}, db[2][4] = {};
                const uint32_t ONE2 = 0x3F803F80u;
                if (kh == 0) { WAIT(B_WMFULL, 0); gemv_part(sb + OFF_Y + HALF, 1, warp, lane); warp_arrive(BAR(B_GEMV)); }
#pragma unroll
                for (int kb = 0; kb < 7; kb++) {
                    WAIT(B_XFULL + kb, 0);
#pragma unroll
                    for (int k4 = 0; k4 < 4; k4++) ldsm4(sb + OFF_X + mrow + kb * 16384 + (((2 * k4) ^ lx) << 4), h + 16 * kb + 4 * k4);
#pragma unroll
                    for (int k4 = 0; k4 < 4; k4++) {
                        const uint32_t* f = h + 16 * kb + 4 * k4;
                        mma16816(ds, f[0], f[1], f[2], f[3], ONE2, ONE2);
                        mma1688(da[0], f[0], f[1], f[0]); mma1688(db[0], f[0], f[1], f[1]);
                        mma1688(da[1], f[2], f[3], f[2]); mma1688(db[1], f[2], f[3], f[3]);
                    }
                }
#pragma unroll
                for (int i = 0; i < 4; i++) {
                    const int ch = 7 * j + 2 * i + (lane >> 4);
                    ldsm4(sb + OFF_X + mrow + (ch >> 3) * 16384 + (((ch ^ lane) & 7) << 4), xr + 4 * i);
                }
                warp_arrive(BAR(B_XFREE));
                float qa = (lr & 1) ? da[0][1] + da[1][1] : da[0][0] + da[1][0];
                float qb = (lr & 1) ? db[0][3] + db[1][3] : db[0][2] + db[1][2];
                const int src = (lane & ~3) | (lr >> 1);
                qa = __shfl_sync(~0u, qa, src);
                qb = __shfl_sync(~0u, qb, src);
                uint32_t ra2, na2, rb2, nb2;
                ln_coeffs(ds[0] * (1.f / DM), qa * (1.f / DM), ra2, na2);
                ln_coeffs(ds[2] * (1.f / DM), qb * (1.f / DM), rb2, nb2);
#pragma unroll
                for (int i = 0; i < 112; i += 2) { h[i] = hfma2(h[i], ra2, na2); h[i + 1] = hfma2(h[i + 1], rb2, nb2); }
                if (kh == 1) { WAIT(B_WMFULL, 0); gemv_part(sb + OFF_Y + HALF, 2, warp, lane); warp_arrive(BAR(B_GEMV)); }
            } else { reg_def<112>(h); reg_def<16>(xr); }
            PROFC(1);
            if (RUN(1)) {
                float ak[28], av[28], aq[28];
                uint32_t kp[14], vp[14];
                const uint32_t bk0 = mkdesc(sb + OFF_Y, DB128) + kh, bv0 = mkdesc(sb + OFF_Y + HALF, DB128) + kh, bq0 = mkdesc(sb + OFF_X, DB128) + kh;
                uint32_t* kvg = act + RB_KV + j * 7168 + (8 * w + 2 * wi) * 224 + lane;
                WAIT(B_FULLK, 0);
                WAIT(B_MOD1, 0);
                PROFC(2);
                reg_def<28>(ak);
#pragma unroll
                for (int g4 = 0; g4 < 4; g4++) {
#pragma unroll
                    for (int ks = 7 * g4; ks < 7 * g4 + 7; ks++) {
                        const uint4 st = *(const uint4*)(smem + M_ST + ks * 64 + q * 16);
                        h[4 * ks] = hfma2(h[4 * ks], st.x, st.y); h[4 * ks + 1] = hfma2(h[4 * ks + 1], st.x, st.y);
                        h[4 * ks + 2] = hfma2(h[4 * ks + 2], st.z, st.w); h[4 * ks + 3] = hfma2(h[4 * ks + 3], st.z, st.w);
                    }
                    WG_FENCE();
#pragma unroll
                    for (int ks = 7 * g4; ks < 7 * g4 + 7; ks++) wgmma_rs_56<DB128>(ak, h[4 * ks], h[4 * ks + 1], h[4 * ks + 2], h[4 * ks + 3], bk0 + ks * 128, ks != 0);
                }
                WG_COMMIT();
                PROFC(3);
                WAIT(B_FULLV, 0);
                reg_def<28>(av);
                WG_FENCE();
#pragma unroll
                for (int ks = 0; ks < 8; ks++) wgmma_rs_56<DB128>(av, h[4 * ks], h[4 * ks + 1], h[4 * ks + 2], h[4 * ks + 3], bv0 + ks * 128, ks != 0);
                WG_COMMIT();
                WG_WAIT(1);
                reg_fence<28>(ak);
#pragma unroll
                for (int g = 0; g < 7; g++) {
                    kp[2 * g] = pack2(ak[4 * g], ak[4 * g + 1]); kp[2 * g + 1] = pack2(ak[4 * g + 2], ak[4 * g + 3]);
                    kvg[g * 32] = kp[2 * g]; kvg[224 + g * 32] = kp[2 * g + 1];
                }
                warp_arrive(BAR(B_PUB));
                PROFC(4);
                WG_FENCE();
#pragma unroll
                for (int ks = 8; ks < 28; ks++) wgmma_rs_56<DB128>(av, h[4 * ks], h[4 * ks + 1], h[4 * ks + 2], h[4 * ks + 3], bv0 + ks * 128, 1);
                WG_COMMIT();
                WAIT(B_FULLQ, 0);
                reg_def<28>(aq);
                WG_FENCE();
#pragma unroll
                for (int ks = 0; ks < 8; ks++) wgmma_rs_56<DB128>(aq, h[4 * ks], h[4 * ks + 1], h[4 * ks + 2], h[4 * ks + 3], bq0 + ks * 128, ks != 0);
                WG_COMMIT();
                WG_WAIT(1);
                reg_fence<28>(av);
#pragma unroll
                for (int g = 0; g < 7; g++) {
                    vp[2 * g] = pack2(av[4 * g], av[4 * g + 1]); vp[2 * g + 1] = pack2(av[4 * g + 2], av[4 * g + 3]);
                    kvg[3584 + g * 32] = vp[2 * g]; kvg[3584 + 224 + g * 32] = vp[2 * g + 1];
                }
                warp_arrive(BAR(B_PUB + 1));
                PROFC(5);
                WG_FENCE();
#pragma unroll
                for (int ks = 8; ks < 28; ks++) wgmma_rs_56<DB128>(aq, h[4 * ks], h[4 * ks + 1], h[4 * ks + 2], h[4 * ks + 3], bq0 + ks * 128, 1);
                WG_COMMIT();
                WAIT(B_PUB + 1, 0);
                const uint32_t ko = sb + OFF_Y + Y_KOWN + (8 * w + 2 * wi) * 896 + lane * 4;
                const uint32_t qo = sb + OFF_Y + Y_Q + (8 * w + 2 * wi) * 1024 + lane * 4;
#pragma unroll
                for (int g = 0; g < 7; g++) {
                    sts1(ko + g * 128, kp[2 * g]); sts1(ko + 896 + g * 128, kp[2 * g + 1]);
                    sts1(ko + (Y_VOWN - Y_KOWN) + g * 128, vp[2 * g]); sts1(ko + (Y_VOWN - Y_KOWN) + 896 + g * 128, vp[2 * g + 1]);
                }
                WG_WAIT(0);
                reg_fence<28>(aq);
                __syncwarp();
                if (lane < 3 && w == 1) mbar_arrive(BAR(B_EMPTY + lane));
#pragma unroll
                for (int g = 0; g < 7; g++) {
                    const uint32_t q0 = pack2(aq[4 * g], aq[4 * g + 1]), q1 = pack2(aq[4 * g + 2], aq[4 * g + 3]);
                    if (g == 3) {
                        sts1(qo + 3 * 128, q < 2 ? q0 : 0u); sts1(qo + 1024 + 3 * 128, q < 2 ? q1 : 0u);
                        sts1(qo + 4 * 128, q < 2 ? 0u : q0); sts1(qo + 1024 + 4 * 128, q < 2 ? 0u : q1);
                    } else {
                        const int ch = g < 3 ? g : g + 1;
                        sts1(qo + ch * 128, q0); sts1(qo + 1024 + ch * 128, q1);
                    }
                }
                if (!sc) bar_sync(3, 256);
            }
        }
        PROFC(6);
        WAIT(B_KRFULL, 0);
        PROFC(7);
        if (RUN(2)) {
#pragma unroll 1
            for (int hf = sc; hf < 2; hf++) {
                COORDS
                float s[136];
                float na = 0.f, nb = 0.f;
                const float CS = 0.18898223650461361f * 1.4426950408889634f;
                const int kg0 = 8 * hf + 2 * wi;
                const int pmin = 16 - 8 * r - 4 * hf - wi;
                const float NEG = __int_as_float(0xFF800000);
                {
                    uint32_t F[8];
                    const uint32_t qa = sb + OFF_Y + Y_Q + (kg0 + ((lane >> 3) & 1)) * 1024 + (4 * w + (lane >> 4)) * 128 + (lane & 7) * 16;
                    ldsm4(qa, F); ldsm4(qa + 256, F + 4);
                    uint32_t ka = sb + OFF_Y + Y_K + kg0 * 896 + (3 * w + (lane >> 3)) * 128 + (lane & 7) * 16;
#pragma unroll
                    for (int g = 0; g < 34; g++) {
                        uint32_t B[4];
                        if (g >= 12 && g % 4 == 0) ka += __float_as_uint(s[4 * (g - 12)]) & p.zero;
                        ldsm4(ka + g * 896, B);
                        mma16816_first(s + 4 * g, F[0], F[1], F[2], F[3], B[0], B[1]);
                        mma16816_v(s + 4 * g, F[4], F[5], F[6], F[7], B[2], B[3]);
                    }
                    const bool c0 = 2 * q > lr, c1 = 2 * q + 1 > lr;
                    if (!c0) { s[0] = NEG; s[6] = NEG; }
                    if (!c1) { s[1] = NEG; s[7] = NEG; }
                    s[2] = NEG; s[3] = NEG;
                    if (c0) { s[128] = NEG; s[134] = NEG; }
                    if (c1) { s[129] = NEG; s[135] = NEG; }
                    s[132] = NEG; s[133] = NEG;
                    float ma = NEG, mb = NEG;
#pragma unroll
                    for (int pp = 0; pp < 17; pp++) {
                        const float* e = s + 8 * pp;
                        const float bias = pp < pmin ? NEG : 0.f;
                        ma = fmaxf(ma, fmaxf(fmaxf(e[0], e[1]), fmaxf(e[4], e[5])) + bias);
                        mb = fmaxf(mb, fmaxf(fmaxf(e[2], e[3]), fmaxf(e[6], e[7])) + bias);
                    }
                    ma = fmaxf(ma, __shfl_xor_sync(~0u, ma, 1)); mb = fmaxf(mb, __shfl_xor_sync(~0u, mb, 1));
                    ma = fmaxf(ma, __shfl_xor_sync(~0u, ma, 2)); mb = fmaxf(mb, __shfl_xor_sync(~0u, mb, 2));
                    na = -ma * CS; nb = -mb * CS;
                }
                PROFC(8 + 3 * hf);
                {
                    WAIT(B_VRFULL, 0);
                    float o[16] = {}, rs[4] = {};
                    uint32_t pk[2];
                    const uint32_t va = sb + OFF_Y + Y_VR + (kg0 + ((lane >> 3) & 1)) * 896 + (3 * w + (lane >> 4)) * 128 + (lane & 7) * 16;
#pragma unroll
                    for (int pp = 0; pp < 17; pp++) {
                        uint32_t B[8];
                        const uint32_t v = va + pp * 1792 + (pp == 16 || (pp >= 9 && kg0 + 2 * pp >= 32) ? Y_VOWN - 32 * 896 : 0);
                        ldsm4t(v, B); ldsm4t(v + 256, B + 4);
                        float e[8];
                        const float bias = __uint_as_float((pp < pmin ? 0xFF800000u : 0u) | ((pp < 2 ? B[0] : pk[pp & 1]) & p.zero));
#pragma unroll
                        for (int i = 0; i < 8; i++) e[i] = ex2(fmaf(s[8 * pp + i], CS, ((i & 2) ? nb : na) + bias));
                        const uint32_t p0 = pack2(e[0], e[1]), p1 = pack2(e[2], e[3]), p2 = pack2(e[4], e[5]), p3 = pack2(e[6], e[7]);
                        pk[pp & 1] = p3;
                        mma16816(rs, p0, p1, p2, p3, 0x3F803F80u, 0x3F803F80u);
#pragma unroll
                        for (int g = 0; g < 4; g++) mma16816(o + 4 * g, p0, p1, p2, p3, B[2 * g], B[2 * g + 1]);
                    }
                    PROFC(9 + 3 * hf);
                    const float ia = rcp(rs[0]), ib = rcp(rs[2]);
                    uint32_t* og = act + RB_O + hf * 14336 + (7 * j + 3 * w) * 256 + wi * 64 + lane;
#pragma unroll
                    for (int g = 0; g < 4; g++) {
                        if ((g == 3 - 3 * w) ? ((q >> 1) == w) : true) {
                            og[g * 256] = pack2(o[4 * g] * ia, o[4 * g + 1] * ia);
                            og[g * 256 + 32] = pack2(o[4 * g + 2] * ib, o[4 * g + 3] * ib);
                        }
                    }
                    warp_arrive(BAR(B_PUB + 2 + hf));
                    PROFC(10 + 3 * hf);
                }
            }
        }
        uint32_t x1p[14];
        COORDS
        constexpr uint64_t DT = dconst(1024, 128, 0);
        const int tile = opaque((lds1(sb + M_EPOCH) & 1) * 2 + w);
        if (RUN(4)) {
            float ac[28];
            const uint32_t ad = mkdesc(sb + (w ? OFF_Y + HALF : OFF_X), DT), bd = mkdesc(sb + OFF_X + HALF, DB128) + kh;
            WAIT(B_WOFULL, 0);
            WAIT(B_MOD2, 0);
            WAIT(B_GFULL + w, 0);
            PROFC(28);
            reg_def<28>(ac);
#pragma unroll 1
            for (int u = 0; u < 4; u++) {
                if (u == 2) WAIT(B_XFULL + 2 + w, 1);
                WG_FENCE();
#pragma unroll
                for (int i = 0; i < 7; i++) wgmma_ss_56<DT, DB128>(ac, ad + (7 * u + i) * 128, bd + (7 * u + i) * 128, (u | i) != 0);
            }
            WG_COMMIT();
            WG_WAIT(0);
            reg_fence<28>(ac);
            PROFC(14);
            __syncwarp();
            if (lane < 3) mbar_arrive(BAR(B_EMPTY + 3 + lane));
            if (lane < 3 && w == 0) mbar_arrive(BAR(B_EMPTY + lane));
            float s1a = 0.f, s2a = 0.f, s1b = 0.f, s2b = 0.f;
            uint32_t* xo = act + RB_X1 + tile * 14336 + 7 * j * 256 + wi * 64 + lane;
#pragma unroll
            for (int g = 0; g < 7; g++) {
                const float2 ga = *(const float2*)(smem + M_G + (8 * g + 2 * q) * 4);
                x1p[2 * g] = pack2(fmaf(ga.x, ac[4 * g], bf_lo(xr[2 * g])), fmaf(ga.y, ac[4 * g + 1], bf_hi(xr[2 * g])));
                x1p[2 * g + 1] = pack2(fmaf(ga.x, ac[4 * g + 2], bf_lo(xr[2 * g + 1])), fmaf(ga.y, ac[4 * g + 3], bf_hi(xr[2 * g + 1])));
                st_relaxed(xo + g * 256, max(x1p[2 * g], 1u)); st_relaxed(xo + g * 256 + 32, max(x1p[2 * g + 1], 1u));
                const float u0 = bf_lo(x1p[2 * g]), u1 = bf_hi(x1p[2 * g]), u2 = bf_lo(x1p[2 * g + 1]), u3 = bf_hi(x1p[2 * g + 1]);
                s1a += u0 + u1; s2a += u0 * u0 + u1 * u1; s1b += u2 + u3; s2b += u2 * u2 + u3 * u3;
            }
            float ka = (q & 1) ? s2a : s1a, kb2 = (q & 1) ? s2b : s1b;
            ka += __shfl_xor_sync(~0u, (q & 1) ? s1a : s2a, 1); kb2 += __shfl_xor_sync(~0u, (q & 1) ? s1b : s2b, 1);
            const float kk = ((q & 2) ? kb2 : ka) + __shfl_xor_sync(~0u, (q & 2) ? ka : kb2, 2);
            st_relaxed(act + RB_ST + ((tile * 8 + j) * 64 + 16 * wi + lr + 4 * (q & 2)) * 2 + (q & 1), max(__float_as_uint(kk), 1u));
            __syncwarp();
            if (lane < 2) mbar_arrive(BAR(B_PUB + 4 + w));
        } else reg_def<14>(x1p);
        PROFC(15);
        uint32_t h2a[32], h2b[24];
        {
            const int fa = pass_f(fs, 0), fb = pass_f(fs, 1), fc = pass_f(fs, 2);
            uint32_t* h2g = act + RB_H2 + (8 * w + 2 * wi) * 32 + lane;
            const uint32_t a0 = mkdesc(sb + OFF_Y + w * HALF, DT);
            if (RUN(3)) {
                WAIT(B_GFULL + 2 + w, 0);
                PROFC(16);
                float2 sa, sbb;
                {
                    uint2 u[16];
#pragma unroll
                    for (int i = 0; i < 16; i++) { const float2 v = lds2f(sb + OFF_X + X_STAT + w * 4096 + ((i >> 1) * 64 + 16 * wi + lr + 8 * (i & 1)) * 8); u[i] = make_uint2(__float_as_uint(v.x), __float_as_uint(v.y)); }
#pragma unroll 1
                    for (;;) {
                        uint32_t mn = ~0u;
#pragma unroll
                        for (int i = 0; i < 16; i++) mn = min(mn, min(u[i].x, u[i].y));
                        if (!__any_sync(~0u, mn == 0u) || sc) break;
#pragma unroll
                        for (int i = 0; i < 16; i++) u[i] = ld_relaxed2(act + RB_ST + ((tile * 8 + (i >> 1)) * 64 + 16 * wi + lr + 8 * (i & 1)) * 2);
                    }
                    sa = make_float2(0.f, 0.f); sbb = sa;
#pragma unroll
                    for (int i = 0; i < 16; i += 2) {
                        sa.x += __uint_as_float(u[i].x); sa.y += __uint_as_float(u[i].y);
                        sbb.x += __uint_as_float(u[i + 1].x); sbb.y += __uint_as_float(u[i + 1].y);
                    }
                }
                warp_arrive(BAR(B_EMPTY + 6));
                uint32_t ra2, na2, rb2, nb2;
                ln_coeffs(sa.x * (1.f / DM), sa.y * (1.f / DM), ra2, na2);
                ln_coeffs(sbb.x * (1.f / DM), sbb.y * (1.f / DM), rb2, nb2);
                const uint32_t ha = sb + OFF_Y + w * HALF + (lane >> 4) * 1024 + (2 * wi + ((lane >> 3) & 1)) * 128 + (lane & 7) * 16;
                const uint32_t sta = sb + M_ST + q * 16;
                const uint32_t* xg = act + RB_X1 + tile * 14336 + wi * 64 + lane;
                uint32_t x[8];
                uint4 st[2];
                auto load = [&](int s) {
                    if (s == 4) WAIT(B_XFULL + 4 + w, 1);
                    ldsm4(ha + s * 4096, x); ldsm4(ha + s * 4096 + 2048, x + 4);
                    st[0] = lds4(sta + s * 128); st[1] = lds4(sta + s * 128 + 64);
                };
                auto prep = [&](int s, uint32_t* f) {
                    while (__any_sync(~0u, min(min(min(x[0], x[1]), min(x[2], x[3])), min(min(x[4], x[5]), min(x[6], x[7]))) == 0u) && !sc) {
#pragma unroll
                        for (int i = 0; i < 8; i++) x[i] = ld_relaxed(xg + (4 * s + (i >> 1)) * 256 + (i & 1) * 32);
                    }
#pragma unroll
                    for (int i = 0; i < 2; i++) {
                        f[4 * i] = hfma2(hfma2(x[4 * i], ra2, na2), st[i].x, st[i].y); f[4 * i + 1] = hfma2(hfma2(x[4 * i + 1], rb2, nb2), st[i].x, st[i].y);
                        f[4 * i + 2] = hfma2(hfma2(x[4 * i + 2], ra2, na2), st[i].z, st[i].w); f[4 * i + 3] = hfma2(hfma2(x[4 * i + 3], rb2, nb2), st[i].z, st[i].w);
                    }
                    if (s < 13) load(s + 1);
                    stsm4(ha + s * 4096, f[0], f[1], f[2], f[3]); stsm4(ha + s * 4096 + 2048, f[4], f[5], f[6], f[7]);
                };
                float ac[128];
                uint32_t fr[3][8];
                const uint32_t bx = mkdesc(sb, DB128);
                reg_def<128>(ac);
                load(0);
                prep(0, fr[0]);
                PROFC(17);
#pragma unroll
                for (int s = 0; s < 14; s++) {
                    {
                        const uint32_t* f = fr[s % 3];
                        const uint32_t bd = bx + (slot_off(s % 7) >> 4);
                        WAIT(B_FULL + s % 7, s >= 7);
                        WG_FENCE();
                        wgmma_rs_256<DB128>(ac, f[0], f[1], f[2], f[3], bd, s != 0);
                        wgmma_rs_256<DB128>(ac, f[4], f[5], f[6], f[7], bd + 128, 1);
                        WG_COMMIT();
                        if (s < 13) prep(s + 1, fr[(s + 1) % 3]);
                        if (s > 0) { WG_WAIT(1); warp_arrive(BAR(B_EMPTY + (s - 1) % 7)); }
                    }
                }
                PROFC(18);
                fence_async_smem();
                WG_WAIT(0);
                reg_fence<128>(ac);
                warp_arrive(BAR(B_EMPTY + 6));
#pragma unroll
                for (int g = 0; g < 16; g++) {
                    h2a[2 * g] = hmul2(pack2_relu(ac[4 * g], ac[4 * g + 1]), pack2(ac[64 + 4 * g], ac[64 + 4 * g + 1]));
                    h2a[2 * g + 1] = hmul2(pack2_relu(ac[4 * g + 2], ac[4 * g + 3]), pack2(ac[64 + 4 * g + 2], ac[64 + 4 * g + 3]));
                    h2g[(fa / 8 + g) * 512] = h2a[2 * g]; h2g[(fa / 8 + g) * 512 + 32] = h2a[2 * g + 1];
                }
                warp_arrive(BAR(B_PUB + 6));
                bar_sync(1 + w, 128);
            } else reg_def<32>(h2a);
            PROFC(19);
            if (RUN(5)) {
                float ac[64];
                reg_def<64>(ac);
                const uint32_t bx = mkdesc(sb, dconst(8192, 1024, 1));
#pragma unroll kB
                for (int s = 0; s < 7; s++) {
                    WAIT(B_FULL + s, 0);
                    const uint32_t ad = a0 + s * 512, bd = bx + (slot_off(s) >> 4);
                    WG_FENCE();
#pragma unroll
                    for (int k = 0; k < 4; k++) wgmma_ss_128<DT, DB128>(ac, ad + k * 128, bd + k * 128, (s | k) != 0);
                    WG_COMMIT();
                    if (s > 0) { WG_WAIT(1); warp_arrive(BAR(B_EMPTY + s - 1)); }
                }
                WG_WAIT(0);
                reg_fence<64>(ac);
                warp_arrive(BAR(B_EMPTY + 6));
#pragma unroll
                for (int g = 0; g < 8; g++) {
                    h2b[2 * g] = hmul2(pack2_relu(ac[4 * g], ac[4 * g + 1]), pack2(ac[32 + 4 * g], ac[32 + 4 * g + 1]));
                    h2b[2 * g + 1] = hmul2(pack2_relu(ac[4 * g + 2], ac[4 * g + 3]), pack2(ac[32 + 4 * g + 2], ac[32 + 4 * g + 3]));
                    h2g[(fb / 8 + g) * 512] = h2b[2 * g]; h2g[(fb / 8 + g) * 512 + 32] = h2b[2 * g + 1];
                }
                warp_arrive(BAR(B_PUB + 7));
            } else reg_def<16>(h2b);
            PROFC(27);
            if (RUN(6)) {
                float ac[32];
                reg_def<32>(ac);
                const uint32_t bx = mkdesc(sb, dconst(4096, 512, 2));
#pragma unroll kC
                for (int s = 0; s < 7; s++) {
                    WAIT(B_FULL + s, 1);
                    const uint32_t ad = a0 + p.zero + s * 512, bd = bx + (slot_off(s) >> 4);
                    WG_FENCE();
#pragma unroll
                    for (int k = 0; k < 4; k++) wgmma_ss_64<DT, dconst(4096, 512, 2)>(ac, ad + k * 128, bd + k * 64, (s | k) != 0);
                    WG_COMMIT();
                    if (s > 0) { WG_WAIT(1); warp_arrive(BAR(B_EMPTY + s - 1)); }
                }
                WG_WAIT(0);
                reg_fence<32>(ac);
                __syncwarp();
                if (lane < 6) mbar_arrive(BAR(B_EMPTY + 6 + lane));
                PROFC(20);
#pragma unroll
                for (int g = 0; g < 4; g++) {
                    h2b[16 + 2 * g] = hmul2(pack2_relu(ac[4 * g], ac[4 * g + 1]), pack2(ac[16 + 4 * g], ac[16 + 4 * g + 1]));
                    h2b[16 + 2 * g + 1] = hmul2(pack2_relu(ac[4 * g + 2], ac[4 * g + 3]), pack2(ac[16 + 4 * g + 2], ac[16 + 4 * g + 3]));
                    h2g[(fc / 8 + g) * 512] = h2b[16 + 2 * g]; h2g[(fc / 8 + g) * 512 + 32] = h2b[16 + 2 * g + 1];
                }
                warp_arrive(BAR(B_PUB + 8));
                asm volatile("barrier.cluster.wait.aligned;" ::: "memory");
                if (lane == 0 && !sc) {
                    uint32_t rb;
                    asm volatile("mapa.shared::cluster.u32 %0, %1, %2;" : "=r"(rb) : "r"(BAR(B_PEER)), "r"(kh ^ 1));
                    asm volatile("mbarrier.arrive.relaxed.cluster.shared::cluster.b64 _, [%0];" ::"r"(rb) : "memory");
                }
            } else reg_def<8>(h2b + 16);
        }
        PROFC(21);
        if (RUN(7)) {
            float ac[56];
            reg_def<56>(ac);
            constexpr uint64_t DAN = dconst(2048, 128, 0);
            constexpr uint64_t DW = dconst(128, 512, 0);
            const uint32_t bx = mkdesc(sb, DW);
#pragma unroll
            for (int e = 0; e < 4; e++) {
                WAIT(B_FULL + e, 0);
                const uint32_t bd = bx + (slot_off(e) >> 4);
                const uint32_t* hh = e < 2 ? h2a + 16 * e : h2b + 16 * (e - 2);
                WG_FENCE();
#pragma unroll
                for (int k = 0; k < (e < 3 ? 4 : 2); k++) wgmma_rs_112<DW>(ac, hh[4 * k], hh[4 * k + 1], hh[4 * k + 2], hh[4 * k + 3], bd + (k >> 1) * 512 + (k & 1) * 16, (e | k) != 0);
                WG_COMMIT();
                if (e > 0) { WG_WAIT(1); warp_arrive(BAR(B_EMPTY + e - 1)); }
            }
            PROFC(22);
            const uint32_t ax = mkdesc(sb + 8192 + w * 1024, DAN);
#pragma unroll kG2
            for (int e = 4; e < 25; e++) {
                WAIT(B_FULL + e % 12, e >= 12 && e < 24);
                if (e == 16) PROFC(23);
                const uint32_t z = (e / 12) * p.zero;
                const uint32_t ad = ax + z + (slot_off(e % 12) >> 4), bd = bx + z + (slot_off(e % 12) >> 4);
                WG_FENCE();
                wgmma_ss_112<DAN, DW>(ac, ad, bd, 1);
                wgmma_ss_112<DAN, DW>(ac, ad + 256, bd + 16, 1);
                WG_COMMIT();
                if (e < 14) { WG_WAIT(1); warp_arrive(BAR(B_EMPTY + (e - 1) % 12)); }
            }
            mbar_wait_cluster(BAR(B_PEER), sc);
            WG_WAIT(0);
            reg_fence<56>(ac);
            PROFC(24);
            uint32_t rdst, rbar;
            asm volatile("mapa.shared::cluster.u32 %0, %1, %2;" : "=r"(rdst) : "r"(sb + OFF_Y + (5 + w) * 16384 + t * 16), "r"(kh ^ 1 ^ sc));
            asm volatile("mapa.shared::cluster.u32 %0, %1, %2;" : "=r"(rbar) : "r"(BAR(B_XCH + w)), "r"(kh ^ 1 ^ sc));
#define ACG(g, i) ac[4 * (g) + (i)]
#pragma unroll
            for (int g = 0; g < 7; g++) {
                const float v0 = kh ? ACG(g, 0) : ACG(g + 7, 0), v1 = kh ? ACG(g, 1) : ACG(g + 7, 1);
                const float v2 = kh ? ACG(g, 2) : ACG(g + 7, 2), v3 = kh ? ACG(g, 3) : ACG(g + 7, 3);
                if (!sc) asm volatile("st.async.shared::cluster.mbarrier::complete_tx::bytes.v4.f32 [%0], {%1,%2,%3,%4}, [%5];"
                             ::"r"(rdst + g * 2048), "f"(v0), "f"(v1), "f"(v2), "f"(v3), "r"(rbar) : "memory");
            }
            mbar_wait_cluster(BAR(B_XCH + w), sc);
            PROFC(25);
            bf16* og = (sc ? (bf16*)act : p.out + (size_t)128 * r * DM) + (size_t)ra * DM + 56 * j + 2 * q;
#pragma unroll
            for (int g = 0; g < 7; g++) {
                const uint4 rv = *(const uint4*)(smem + OFF_Y + (5 + w) * 16384 + t * 16 + g * 2048);
                const float2 gb = *(const float2*)(smem + M_G + 224 + (8 * g + 2 * q) * 4);
                const float v0 = (kh ? ACG(g + 7, 0) : ACG(g, 0)) + __uint_as_float(rv.x), v1 = (kh ? ACG(g + 7, 1) : ACG(g, 1)) + __uint_as_float(rv.y);
                const float v2 = (kh ? ACG(g + 7, 2) : ACG(g, 2)) + __uint_as_float(rv.z), v3 = (kh ? ACG(g + 7, 3) : ACG(g, 3)) + __uint_as_float(rv.w);
                *(uint32_t*)(og + 8 * g) = pack2(fmaf(gb.x, v0, bf_lo(x1p[2 * g])), fmaf(gb.y, v1, bf_hi(x1p[2 * g])));
                *(uint32_t*)(og + 8 * DM + 8 * g) = pack2(fmaf(gb.x, v2, bf_lo(x1p[2 * g + 1])), fmaf(gb.y, v3, bf_hi(x1p[2 * g + 1])));
            }
        }
        PROFC(26);
        bar_sync(1 + w, 128);
        if (wi == 0) warp_arrive(BAR(B_DONE));
    } else {
        const int lane = fresh_tid() & 31;
        const bool early = kh == 0, gemv = r < 14;
        const int mcol = early ? 16 * (4 * r + nq) : 2 * DM + 32 * (4 * r + nq);
        const uint32_t wmbuf = sb + OFF_Y + HALF;
        asm volatile("setmaxnreg.dec.sync.aligned.u32 56;");
        if (warp == 9) {
#pragma unroll
            for (int i = 56; i < 64; i++) init_e(BAR(i), 1);
            fence_async_smem();
        }
        if (warp == 8) { init_e(BAR(B_WMFULL), 2); fence_async_smem(); }
        bar_arrive(0, 384);
        asm volatile("barrier.cluster.arrive.relaxed.aligned;" ::: "memory");
        uint32_t target = 0;
        if (warp == 8) {
            if (!sc) {
                expect_e(BAR(B_WMFULL), gemv ? 28672 >> early : 0);
                if (early && gemv) { tma3_e(wmbuf, &p.wm, mcol, 0, 0, BAR(B_WMFULL)); tma3_e(wmbuf + 7168, &p.wm, mcol, 224, 0, BAR(B_WMFULL)); }
#pragma unroll 1
                for (int kb = 0; kb < 7; kb++) {
                    expect_e(BAR(B_XFULL + kb), 16384);
                    tma3_e(sb + OFF_X + kb * 16384, &p.xm, 64 * kb, 128 * r, 0, BAR(B_XFULL + kb));
                }
            }
#pragma unroll 1
            for (int mt = 0; mt < 4; mt++) {
                if (mt == 1) {
                    if (!early && gemv) {
#pragma unroll 1
                        for (int k = 0; k < 4; k++) tma3_e(wmbuf + k * 7168, &p.wm, mcol + (k >> 1) * 16, (k & 1) * 224, 0, BAR(B_WMFULL));
                    }
                    bar_sync(9, 384);
                    if (sc) return;
                    mbar_wait(BAR(B_MOD1), 0);
                    mbar_wait(BAR(B_WMFREE), 0);
                }
                if (mt == 2) mbar_wait(BAR(B_XFREE), 0);
                if (mt == 3) mbar_wait(BAR(B_VRFULL), 0);
                const uint32_t bar = BAR(mt == 3 ? B_WOFULL : B_FULLK + mt), dst = sb + (mt < 2 ? OFF_Y : OFF_X) + (mt & 1) * HALF;
                const int c0 = (mt < 2 ? DM + DM * mt : 0) + 56 * j - 8 * kh;
                if (!sc) {
                    expect_e(bar, HALF);
                    tma3_e(dst, mt == 3 ? &p.wo : &p.qkv, c0, 0, 0, bar);
                    tma3_e(dst + HALF / 2, mt == 3 ? &p.wo : &p.qkv, c0, 224, 0, bar);
                }
            }
            expect_e(BAR(B_XCH), 14336);
            expect_e(BAR(B_XCH + 1), 14336);
        } else {
            if (warp == 10 && !sc) {
                l2_prefetch_e((const char*)p.wqkv + (size_t)b * 9408, 9408);
                if (lane == 0) sts1(sb + M_EPOCH, atomicAdd(&g_ticket, 1u) / NCTA);
            }
            if (warp == 11) {
#pragma unroll
                for (int i = 0; i < 8; i++) {
                    const int wd = lane + 32 * i;
                    const uint32_t cb = i < 7 ? __ldg((const uint32_t*)p.c + wd) : 0u;
                    sts1(wmbuf + 28672 + (wd >> 3) * 32 + (wd & 3) * 8 + (wd & 4), pack2(silu_bf(cb & 0xFFFFu), silu_bf(cb >> 16)));
                }
            }
            bar_sync(9, 384);
            if (sc) return;
            target = lds1(sb + M_EPOCH) + 1;
            const uint32_t tag = target & 0xFFFFu;
            if (warp == 11) {
                warp_arrive(BAR(B_WMFULL));
                mbar_wait(BAR(B_GEMV), 0);
                float sum = 0.f;
#pragma unroll
                for (int i = 0; i < 8; i++) sum += *(const float*)(smem + OFF_Y + HALF + 29696 + (i * 32 + (early ? lane & 15 : lane)) * 4);
                const uint32_t word = (pack2(sum, 0.f) << 16) | tag;
                if (gemv) {
                    uint32_t* mg = g_mod + mcol + (early ? (lane & 15) + (lane >> 4) * 4 * 6 * DM : lane);
#pragma unroll
                    for (int i = 0; i < 8; i++) if (i < 4 || !early) st_relaxed(mg + i * 6 * DM, word);
                }
                warp_arrive(BAR(B_WMFREE));
            }
            const uint4* modp = (const uint4*)g_mod + (r & 7) * (6 * DM / 4);
            const bool p2 = warp == 11;
            mbar_wait(BAR(p2 ? B_PUB : B_XFULL + 4), 0);
#pragma unroll 1
            for (int it = p2 ? 0 : warp - 9; it < (p2 ? 2 : warp - 8); it++) {
                const int i0 = lane + 32 * it, imax = p2 ? 251 : 223;
                uint4 v[4];
#pragma unroll 1
                for (int n = 0;; n++) {
                    uint32_t bad = 0;
#pragma unroll
                    for (int k = 0; k < 4; k++) {
                        const int i = min(i0 + 64 * k, imax);
                        v[k] = ld_relaxed4(modp + (i < 224 ? (p2 ? 336 : 0) + i : (i < 238 ? 14 * j + i : 14 * j + i + 322)));
                        bad |= (v[k].x ^ tag) | (v[k].y ^ tag) | (v[k].z ^ tag) | (v[k].w ^ tag);
                    }
                    if (!__any_sync(~0u, bad & 0xFFFFu)) break;
                    if (n > SPIN_LIMIT) __trap();
                }
#pragma unroll
                for (int k = 0; k < 4; k++) {
                    const int i = min(i0 + 64 * k, imax);
                    if (i < 224) {
                        const int isc = i >= 112, c4 = i - 112 * isc;
                        const float one = isc ? 1.f : 0.f;
                        const uint32_t a = sb + M_ST + (c4 >> 2) * 64 + (c4 & 1) * 32 + (c4 & 2) * 4 + (isc ? 0 : 4);
                        sts1(a, pack2(bf_hi(v[k].x) + one, bf_hi(v[k].y) + one));
                        sts1(a + 16, pack2(bf_hi(v[k].z) + one, bf_hi(v[k].w) + one));
                    } else {
                        sts4(sb + M_G + (i - 224) * 16, make_uint4(v[k].x & 0xFFFF0000u, v[k].y & 0xFFFF0000u, v[k].z & 0xFFFF0000u, v[k].w & 0xFFFF0000u));
                    }
                }
                warp_arrive(BAR(p2 ? B_MOD2 : B_MOD1));
            }
            if (warp == 9) {
#pragma unroll 1
                for (int kv = 0; kv < 2; kv++) {
                    mbar_wait(BAR(B_PUB + kv), 0);
                    wait_flags(g_flag + b * 128 + lane, target, (r >= 2 ? 6u : r == 1 ? 2u : 0u) << (8 * kv));
                    fence_async_global();
                    const uint32_t dst = sb + OFF_Y + (kv ? Y_VR : Y_K);
                    expect_e(BAR(B_KRFULL + kv), r >= 2 ? 28672 : r == 1 ? 14336 : 0);
                    if (r >= 2) bulk_e(dst, act - 2 * RB_WORDS + RB_KV + j * 7168 + kv * 3584, 14336, BAR(B_KRFULL + kv));
                    if (r >= 1) bulk_e(dst + 14336, act - RB_WORDS + RB_KV + j * 7168 + kv * 3584, 14336, BAR(B_KRFULL + kv));
                }
            } else if (warp == 11) {
                mbar_wait(BAR(B_VRFULL), 0);
                l2_prefetch_e((const char*)p.wg + (size_t)b * 12544, 12544);
                l2_prefetch_e((const char*)p.wu + (size_t)b * 12544, 12544);
#pragma unroll 1
                for (int k = 0; k < (r < 12 ? 2 : 1); k++) {
                    const int u = 28 * kh + r + 16 * k;
                    expect_e(BAR(B_XFULL + k), 7168);
                    tma3_e(sb + OFF_Y + 102400, &p.dn, 0, 32 * u, 14 * nq, BAR(B_XFULL + k));
                    mbar_wait(BAR(B_XFULL + k), 1);
                    asm volatile("{\n.reg .pred p;\nelect.sync _|p, 0xffffffff;\n@p cp.async.bulk.global.shared::cta.bulk_group [%0], [%1], 7168;\n"
                                 "cp.async.bulk.commit_group;\ncp.async.bulk.wait_group 0;\n}" ::"l"(g_wd + (size_t)(u * 4 + nq) * 1792), "r"(sb + OFF_Y + 102400) : "memory");
                    __syncwarp();
                }
                warp_arrive(BAR(B_WMFREE));
                fence_gpu();
                if (lane < 16) st_relaxed(g_flag + (8 * lane + j) * 128 + 96 + r, target);
            }
        }
        if (warp == 8 || warp == 11) {
            const int sec = warp == 11;
            if (sec) ring_loader<1>(p, sb, r, j, lane); else ring_loader<0>(p, sb, r, j, lane);
            mbar_wait(BAR(B_DONE), 0);
        } else if (warp == 9) {
#pragma unroll
            for (int ev = 0; ev < 4; ev++) { expect_e(BAR(B_GFULL + ev), ev < 2 ? HALF / 2 : 16384 + 4096); expect_e(BAR(B_XFULL + 2 + ev), ev < 2 ? HALF / 2 : HALF - 16384); }
            mbar_wait(BAR(B_PUB + 2), 0);
            const uint32_t* fp = g_flag + b * 128 + 32 + lane;
            const int par = (target - 1) & 1;
#pragma unroll 1
            for (int n = 0, ev = 0; ev < 4; n++) {
                if (ev == 1) { mbar_wait(BAR(B_WMFREE), 1); mbar_wait(BAR(B_PUB + 3), 0); }
                uint32_t ok = __ballot_sync(~0u, (int)(ld_relaxed(fp) - target) >= 0) >> (8 * ev);
                while ((ok & 0xFFu) == 0xFFu) {
                    asm volatile("fence.acquire.gpu;" ::: "memory");
                    fence_async_global();
                    const int tile = (ev & 1) + (ev >> 1) * par * 2;
                    const uint32_t dst = sb + (ev == 0 ? OFF_X : OFF_Y + (ev & 1) * HALF), first = ev < 2 ? HALF / 2 : 16384;
                    const char* src = (const char*)(act + RB_O + ((ev >> 1) * 2 + tile) * 14336);
                    if (ev >= 2) bulk_e(sb + OFF_X + X_STAT + (ev & 1) * 4096, act + RB_ST + tile * 1024, 4096, BAR(B_GFULL + ev));
                    bulk_e(dst, src, first, BAR(B_GFULL + ev));
                    bulk_e(dst + first, src + first, HALF - first, BAR(B_XFULL + 2 + ev));
                    if (ev) PROFH(4 + ev);
                    ev++; ok >>= 8;
                }
                if (n > SPIN_LIMIT) __trap();
            }
            mbar_wait(BAR(B_XFULL + 5), 1);
#pragma unroll 1
            for (int hf = 0; hf < 2; hf++) {
                const int tile = (par ^ 1) * 2 + hf;
                uint4* xz = (uint4*)(act + RB_X1 + tile * 14336 + j * 1792) + lane;
#pragma unroll
                for (int i = 0; i < 14; i++) xz[i * 32] = make_uint4(0, 0, 0, 0);
                ((uint4*)(act + RB_ST + (tile * 8 + j) * 128))[lane] = make_uint4(0, 0, 0, 0);
            }
#pragma unroll 1
            for (int ps = 0; ps < 3; ps++) {
                mbar_wait(BAR(B_PUB + 6 + ps), 0);
                wait_flags(g_flag + b * 128 + 64 + lane, target, (0x55u << kh) << (8 * ps));
                warp_arrive(BAR(B_HRDY + ps));
                PROFH(9 + ps);
            }
        } else {
#pragma unroll 1
            for (int k = 0; k < 9; k++) {
                uint32_t* fp = k < 2 ? g_flag + (b + 8 * lane) * 128 + k * 8 + lane : g_flag + (8 * r + lane) * 128 + 16 + k * 8 + j;
                mbar_wait(BAR(B_PUB + k), 0);
                if (k != 4 && k != 5) fence_gpu();
                if (k < 2 ? (lane == 1 || lane == 2) : lane < 8) st_relaxed(fp, target);
                if (k >= 3 && k <= 5) PROFH(k - 3);
            }
        }
    }
}

#undef act
typedef CUresult (*EncodeFn)(CUtensorMap*, CUtensorMapDataType, cuuint32_t, void*, const cuuint64_t*, const cuuint64_t*, const cuuint32_t*,
                             const cuuint32_t*, CUtensorMapInterleave, CUtensorMapSwizzle, CUtensorMapL2promotion, CUtensorMapFloatOOBfill);

static void make_map(EncodeFn fn, CUtensorMap* m, const void* ptr, uint64_t d0, uint64_t d1, uint64_t d2, uint64_t s1, uint64_t s2,
                     uint32_t b0, uint32_t b1, uint32_t b2, CUtensorMapSwizzle sw) {
    cuuint64_t dims[3] = {d0, d1, d2}, strides[2] = {s1, s2};
    cuuint32_t box[3] = {b0, b1, b2}, es[3] = {1, 1, 1};
    CUresult rc = fn(m, CU_TENSOR_MAP_DATA_TYPE_BFLOAT16, 3, (void*)ptr, dims, strides, box, es, CU_TENSOR_MAP_INTERLEAVE_NONE, sw,
                     CU_TENSOR_MAP_L2_PROMOTION_L2_128B, CU_TENSOR_MAP_FLOAT_OOB_FILL_NONE);
    (void)rc;
}

extern "C" void kernel_launch(void* const* d_in, const int* in_sizes, int n_in, void* d_out, int out_size) {
    (void)in_sizes; (void)n_in; (void)out_size;
    static EncodeFn fn = nullptr;
    static uint32_t* act_base = nullptr;
    if (!fn) {
        cudaDriverEntryPointQueryResult st;
        cudaGetDriverEntryPoint("cuTensorMapEncodeTiled", (void**)&fn, cudaEnableDefault, &st);
        void* a = nullptr;
        cudaGetSymbolAddress(&a, g_act);
        act_base = (uint32_t*)(((uintptr_t)a + 0xFFFFF) & ~(uintptr_t)0xFFFFF);
        cudaFuncSetAttribute(fused_block_kernel, cudaFuncAttributeMaxDynamicSharedMemorySize, SMEM_BYTES);
    }
    Params p;
    p.x = (const bf16*)d_in[0];
    const bf16* wqkv = (const bf16*)d_in[1];
    p.wqkv = wqkv;
    p.wop = (const bf16*)d_in[2];
    p.wg = (const bf16*)d_in[4];
    p.wu = (const bf16*)d_in[5];
    p.wd = (const bf16*)d_in[6];
    p.c = (const bf16*)d_in[7];
    p.wmod = (const bf16*)d_in[8];
    p.out = (bf16*)d_out;
    p.zero = 0;
    p.actb = act_base;
    make_map(fn, &p.wm, p.wmod, 2688, 448, 1, 5376, 5376 * 448, 16, 224, 1, CU_TENSOR_MAP_SWIZZLE_NONE);
    make_map(fn, &p.xm, p.x, 448, 2048, 1, 896, 896 * 2048, 64, 128, 1, CU_TENSOR_MAP_SWIZZLE_128B);
    make_map(fn, &p.qkv, wqkv, 1344, 448, 1, 2688, 2688 * 448, 64, 224, 1, CU_TENSOR_MAP_SWIZZLE_128B);
    make_map(fn, &p.wo, p.wop, 448, 448, 1, 896, 896 * 448, 64, 224, 1, CU_TENSOR_MAP_SWIZZLE_128B);
    make_map(fn, &p.ga, p.wg, 64, 448, 28, 3584, 128, 64, 32, 2, CU_TENSOR_MAP_SWIZZLE_128B);
    make_map(fn, &p.ua, p.wu, 64, 448, 28, 3584, 128, 64, 32, 2, CU_TENSOR_MAP_SWIZZLE_128B);
    make_map(fn, &p.gb, p.wg, 64, 448, 28, 3584, 128, 64, 64, 1, CU_TENSOR_MAP_SWIZZLE_128B);
    make_map(fn, &p.ub, p.wu, 64, 448, 28, 3584, 128, 64, 64, 1, CU_TENSOR_MAP_SWIZZLE_128B);
    make_map(fn, &p.gc, p.wg, 32, 448, 56, 3584, 64, 32, 64, 1, CU_TENSOR_MAP_SWIZZLE_64B);
    make_map(fn, &p.uc, p.wu, 32, 448, 56, 3584, 64, 32, 64, 1, CU_TENSOR_MAP_SWIZZLE_64B);
    make_map(fn, &p.dn, p.wd, 8, 1792, 56, 896, 16, 8, 32, 14, CU_TENSOR_MAP_SWIZZLE_NONE);
    fused_block_kernel<<<GRID, 384, SMEM_BYTES>>>(p);
}
```

```cpp
#include <cuda_runtime.h>
#include <cuda_bf16.h>
#include <cuda.h>
#include <stdint.h>

typedef __nv_bfloat16 bf16;

template<uint64_t CB> __device__ __forceinline__ void wgmma_rs_56(float* d, uint32_t a0, uint32_t a1, uint32_t a2, uint32_t a3, uint32_t db, int sd) {
  asm volatile("{\n.reg .pred p;\n.reg .b64 b;\nsetp.ne.b32 p, %33, 0;\nmov.b64 b, {%32, %34};\n"
    "wgmma.mma_async.sync.aligned.m64n56k16.f32.bf16.bf16 {%0,%1,%2,%3,%4,%5,%6,%7,%8,%9,%10,%11,%12,%13,%14,%15,%16,%17,%18,%19,%20,%21,%22,%23,%24,%25,%26,%27}, {%28,%29,%30,%31}, b, p, 1, 1, 1;\n}\n"
    : "+f"(d[0]),"+f"(d[1]),"+f"(d[2]),"+f"(d[3]),"+f"(d[4]),"+f"(d[5]),"+f"(d[6]),"+f"(d[7]),"+f"(d[8]),"+f"(d[9]),"+f"(d[10]),"+f"(d[11]),"+f"(d[12]),"+f"(d[13]),"+f"(d[14]),"+f"(d[15]),"+f"(d[16]),"+f"(d[17]),"+f"(d[18]),"+f"(d[19]),"+f"(d[20]),"+f"(d[21]),"+f"(d[22]),"+f"(d[23]),"+f"(d[24]),"+f"(d[25]),"+f"(d[26]),"+f"(d[27])
    : "r"(a0), "r"(a1), "r"(a2), "r"(a3), "r"(db), "r"(sd), "n"((uint32_t)(CB >> 32)));
}
template<uint64_t CA, uint64_t CB> __device__ __forceinline__ void wgmma_ss_56(float* d, uint32_t da, uint32_t db, int sd) {
  asm volatile("{\n.reg .pred p;\n.reg .b64 a, b;\nsetp.ne.b32 p, %30, 0;\nmov.b64 a, {%28, %31};\nmov.b64 b, {%29, %32};\n"
    "wgmma.mma_async.sync.aligned.m64n56k16.f32.bf16.bf16 {%0,%1,%2,%3,%4,%5,%6,%7,%8,%9,%10,%11,%12,%13,%14,%15,%16,%17,%18,%19,%20,%21,%22,%23,%24,%25,%26,%27}, a, b, p, 1, 1, 0, 1;\n}\n"
    : "+f"(d[0]),"+f"(d[1]),"+f"(d[2]),"+f"(d[3]),"+f"(d[4]),"+f"(d[5]),"+f"(d[6]),"+f"(d[7]),"+f"(d[8]),"+f"(d[9]),"+f"(d[10]),"+f"(d[11]),"+f"(d[12]),"+f"(d[13]),"+f"(d[14]),"+f"(d[15]),"+f"(d[16]),"+f"(d[17]),"+f"(d[18]),"+f"(d[19]),"+f"(d[20]),"+f"(d[21]),"+f"(d[22]),"+f"(d[23]),"+f"(d[24]),"+f"(d[25]),"+f"(d[26]),"+f"(d[27])
    : "r"(da), "r"(db), "r"(sd), "n"((uint32_t)(CA >> 32)), "n"((uint32_t)(CB >> 32)));
}
template<uint64_t CB> __device__ __forceinline__ void wgmma_rs_256(float* d, uint32_t a0, uint32_t a1, uint32_t a2, uint32_t a3, uint32_t db, int sd) {
  asm volatile("{\n.reg .pred p;\n.reg .b64 b;\nsetp.ne.b32 p, %133, 0;\nmov.b64 b, {%132, %134};\n"
    "wgmma.mma_async.sync.aligned.m64n256k16.f32.bf16.bf16 {%0,%1,%2,%3,%4,%5,%6,%7,%8,%9,%10,%11,%12,%13,%14,%15,%16,%17,%18,%19,%20,%21,%22,%23,%24,%25,%26,%27,%28,%29,%30,%31,%32,%33,%34,%35,%36,%37,%38,%39,%40,%41,%42,%43,%44,%45,%46,%47,%48,%49,%50,%51,%52,%53,%54,%55,%56,%57,%58,%59,%60,%61,%62,%63,%64,%65,%66,%67,%68,%69,%70,%71,%72,%73,%74,%75,%76,%77,%78,%79,%80,%81,%82,%83,%84,%85,%86,%87,%88,%89,%90,%91,%92,%93,%94,%95,%96,%97,%98,%99,%100,%101,%102,%103,%104,%105,%106,%107,%108,%109,%110,%111,%112,%113,%114,%115,%116,%117,%118,%119,%120,%121,%122,%123,%124,%125,%126,%127}, {%128,%129,%130,%131}, b, p, 1, 1, 1;\n}\n"
    : "+f"(d[0]),"+f"(d[1]),"+f"(d[2]),"+f"(d[3]),"+f"(d[4]),"+f"(d[5]),"+f"(d[6]),"+f"(d[7]),"+f"(d[8]),"+f"(d[9]),"+f"(d[10]),"+f"(d[11]),"+f"(d[12]),"+f"(d[13]),"+f"(d[14]),"+f"(d[15]),"+f"(d[16]),"+f"(d[17]),"+f"(d[18]),"+f"(d[19]),"+f"(d[20]),"+f"(d[21]),"+f"(d[22]),"+f"(d[23]),"+f"(d[24]),"+f"(d[25]),"+f"(d[26]),"+f"(d[27]),"+f"(d[28]),"+f"(d[29]),"+f"(d[30]),"+f"(d[31]),"+f"(d[32]),"+f"(d[33]),"+f"(d[34]),"+f"(d[35]),"+f"(d[36]),"+f"(d[37]),"+f"(d[38]),"+f"(d[39]),"+f"(d[40]),"+f"(d[41]),"+f"(d[42]),"+f"(d[43]),"+f"(d[44]),"+f"(d[45]),"+f"(d[46]),"+f"(d[47]),"+f"(d[48]),"+f"(d[49]),"+f"(d[50]),"+f"(d[51]),"+f"(d[52]),"+f"(d[53]),"+f"(d[54]),"+f"(d[55]),"+f"(d[56]),"+f"(d[57]),"+f"(d[58]),"+f"(d[59]),"+f"(d[60]),"+f"(d[61]),"+f"(d[62]),"+f"(d[63]),"+f"(d[64]),"+f"(d[65]),"+f"(d[66]),"+f"(d[67]),"+f"(d[68]),"+f"(d[69]),"+f"(d[70]),"+f"(d[71]),"+f"(d[72]),"+f"(d[73]),"+f"(d[74]),"+f"(d[75]),"+f"(d[76]),"+f"(d[77]),"+f"(d[78]),"+f"(d[79]),"+f"(d[80]),"+f"(d[81]),"+f"(d[82]),"+f"(d[83]),"+f"(d[84]),"+f"(d[85]),"+f"(d[86]),"+f"(d[87]),"+f"(d[88]),"+f"(d[89]),"+f"(d[90]),"+f"(d[91]),"+f"(d[92]),"+f"(d[93]),"+f"(d[94]),"+f"(d[95]),"+f"(d[96]),"+f"(d[97]),"+f"(d[98]),"+f"(d[99]),"+f"(d[100]),"+f"(d[101]),"+f"(d[102]),"+f"(d[103]),"+f"(d[104]),"+f"(d[105]),"+f"(d[106]),"+f"(d[107]),"+f"(d[108]),"+f"(d[109]),"+f"(d[110]),"+f"(d[111]),"+f"(d[112]),"+f"(d[113]),"+f"(d[114]),"+f"(d[115]),"+f"(d[116]),"+f"(d[117]),"+f"(d[118]),"+f"(d[119]),"+f"(d[120]),"+f"(d[121]),"+f"(d[122]),"+f"(d[123]),"+f"(d[124]),"+f"(d[125]),"+f"(d[126]),"+f"(d[127])
    : "r"(a0), "r"(a1), "r"(a2), "r"(a3), "r"(db), "r"(sd), "n"((uint32_t)(CB >> 32)));
}
template<uint64_t CA, uint64_t CB> __device__ __forceinline__ void wgmma_ss_128(float* d, uint32_t da, uint32_t db, int sd) {
  asm volatile("{\n.reg .pred p;\n.reg .b64 a, b;\nsetp.ne.b32 p, %66, 0;\nmov.b64 a, {%64, %67};\nmov.b64 b, {%65, %68};\n"
    "wgmma.mma_async.sync.aligned.m64n128k16.f32.bf16.bf16 {%0,%1,%2,%3,%4,%5,%6,%7,%8,%9,%10,%11,%12,%13,%14,%15,%16,%17,%18,%19,%20,%21,%22,%23,%24,%25,%26,%27,%28,%29,%30,%31,%32,%33,%34,%35,%36,%37,%38,%39,%40,%41,%42,%43,%44,%45,%46,%47,%48,%49,%50,%51,%52,%53,%54,%55,%56,%57,%58,%59,%60,%61,%62,%63}, a, b, p, 1, 1, 0, 1;\n}\n"
    : "+f"(d[0]),"+f"(d[1]),"+f"(d[2]),"+f"(d[3]),"+f"(d[4]),"+f"(d[5]),"+f"(d[6]),"+f"(d[7]),"+f"(d[8]),"+f"(d[9]),"+f"(d[10]),"+f"(d[11]),"+f"(d[12]),"+f"(d[13]),"+f"(d[14]),"+f"(d[15]),"+f"(d[16]),"+f"(d[17]),"+f"(d[18]),"+f"(d[19]),"+f"(d[20]),"+f"(d[21]),"+f"(d[22]),"+f"(d[23]),"+f"(d[24]),"+f"(d[25]),"+f"(d[26]),"+f"(d[27]),"+f"(d[28]),"+f"(d[29]),"+f"(d[30]),"+f"(d[31]),"+f"(d[32]),"+f"(d[33]),"+f"(d[34]),"+f"(d[35]),"+f"(d[36]),"+f"(d[37]),"+f"(d[38]),"+f"(d[39]),"+f"(d[40]),"+f"(d[41]),"+f"(d[42]),"+f"(d[43]),"+f"(d[44]),"+f"(d[45]),"+f"(d[46]),"+f"(d[47]),"+f"(d[48]),"+f"(d[49]),"+f"(d[50]),"+f"(d[51]),"+f"(d[52]),"+f"(d[53]),"+f"(d[54]),"+f"(d[55]),"+f"(d[56]),"+f"(d[57]),"+f"(d[58]),"+f"(d[59]),"+f"(d[60]),"+f"(d[61]),"+f"(d[62]),"+f"(d[63])
    : "r"(da), "r"(db), "r"(sd), "n"((uint32_t)(CA >> 32)), "n"((uint32_t)(CB >> 32)));
}
template<uint64_t CA, uint64_t CB> __device__ __forceinline__ void wgmma_ss_64(float* d, uint32_t da, uint32_t db, int sd) {
  asm volatile("{\n.reg .pred p;\n.reg .b64 a, b;\nsetp.ne.b32 p, %34, 0;\nmov.b64 a, {%32, %35};\nmov.b64 b, {%33, %36};\n"
    "wgmma.mma_async.sync.aligned.m64n64k16.f32.bf16.bf16 {%0,%1,%2,%3,%4,%5,%6,%7,%8,%9,%10,%11,%12,%13,%14,%15,%16,%17,%18,%19,%20,%21,%22,%23,%24,%25,%26,%27,%28,%29,%30,%31}, a, b, p, 1, 1, 0, 1;\n}\n"
    : "+f"(d[0]),"+f"(d[1]),"+f"(d[2]),"+f"(d[3]),"+f"(d[4]),"+f"(d[5]),"+f"(d[6]),"+f"(d[7]),"+f"(d[8]),"+f"(d[9]),"+f"(d[10]),"+f"(d[11]),"+f"(d[12]),"+f"(d[13]),"+f"(d[14]),"+f"(d[15]),"+f"(d[16]),"+f"(d[17]),"+f"(d[18]),"+f"(d[19]),"+f"(d[20]),"+f"(d[21]),"+f"(d[22]),"+f"(d[23]),"+f"(d[24]),"+f"(d[25]),"+f"(d[26]),"+f"(d[27]),"+f"(d[28]),"+f"(d[29]),"+f"(d[30]),"+f"(d[31])
    : "r"(da), "r"(db), "r"(sd), "n"((uint32_t)(CA >> 32)), "n"((uint32_t)(CB >> 32)));
}
template<uint64_t CA, uint64_t CB> __device__ __forceinline__ void wgmma_ss_112(float* d, uint32_t da, uint32_t db, int sd) {
  asm volatile("{\n.reg .pred p;\n.reg .b64 a, b;\nsetp.ne.b32 p, %58, 0;\nmov.b64 a, {%56, %59};\nmov.b64 b, {%57, %60};\n"
    "wgmma.mma_async.sync.aligned.m64n112k16.f32.bf16.bf16 {%0,%1,%2,%3,%4,%5,%6,%7,%8,%9,%10,%11,%12,%13,%14,%15,%16,%17,%18,%19,%20,%21,%22,%23,%24,%25,%26,%27,%28,%29,%30,%31,%32,%33,%34,%35,%36,%37,%38,%39,%40,%41,%42,%43,%44,%45,%46,%47,%48,%49,%50,%51,%52,%53,%54,%55}, a, b, p, 1, 1, 0, 1;\n}\n"
    : "+f"(d[0]),"+f"(d[1]),"+f"(d[2]),"+f"(d[3]),"+f"(d[4]),"+f"(d[5]),"+f"(d[6]),"+f"(d[7]),"+f"(d[8]),"+f"(d[9]),"+f"(d[10]),"+f"(d[11]),"+f"(d[12]),"+f"(d[13]),"+f"(d[14]),"+f"(d[15]),"+f"(d[16]),"+f"(d[17]),"+f"(d[18]),"+f"(d[19]),"+f"(d[20]),"+f"(d[21]),"+f"(d[22]),"+f"(d[23]),"+f"(d[24]),"+f"(d[25]),"+f"(d[26]),"+f"(d[27]),"+f"(d[28]),"+f"(d[29]),"+f"(d[30]),"+f"(d[31]),"+f"(d[32]),"+f"(d[33]),"+f"(d[34]),"+f"(d[35]),"+f"(d[36]),"+f"(d[37]),"+f"(d[38]),"+f"(d[39]),"+f"(d[40]),"+f"(d[41]),"+f"(d[42]),"+f"(d[43]),"+f"(d[44]),"+f"(d[45]),"+f"(d[46]),"+f"(d[47]),"+f"(d[48]),"+f"(d[49]),"+f"(d[50]),"+f"(d[51]),"+f"(d[52]),"+f"(d[53]),"+f"(d[54]),"+f"(d[55])
    : "r"(da), "r"(db), "r"(sd), "n"((uint32_t)(CA >> 32)), "n"((uint32_t)(CB >> 32)));
}
template<uint64_t CB> __device__ __forceinline__ void wgmma_rs_112(float* d, uint32_t a0, uint32_t a1, uint32_t a2, uint32_t a3, uint32_t db, int sd) {
  asm volatile("{\n.reg .pred p;\n.reg .b64 b;\nsetp.ne.b32 p, %61, 0;\nmov.b64 b, {%60, %62};\n"
    "wgmma.mma_async.sync.aligned.m64n112k16.f32.bf16.bf16 {%0,%1,%2,%3,%4,%5,%6,%7,%8,%9,%10,%11,%12,%13,%14,%15,%16,%17,%18,%19,%20,%21,%22,%23,%24,%25,%26,%27,%28,%29,%30,%31,%32,%33,%34,%35,%36,%37,%38,%39,%40,%41,%42,%43,%44,%45,%46,%47,%48,%49,%50,%51,%52,%53,%54,%55}, {%56,%57,%58,%59}, b, p, 1, 1, 1;\n}\n"
    : "+f"(d[0]),"+f"(d[1]),"+f"(d[2]),"+f"(d[3]),"+f"(d[4]),"+f"(d[5]),"+f"(d[6]),"+f"(d[7]),"+f"(d[8]),"+f"(d[9]),"+f"(d[10]),"+f"(d[11]),"+f"(d[12]),"+f"(d[13]),"+f"(d[14]),"+f"(d[15]),"+f"(d[16]),"+f"(d[17]),"+f"(d[18]),"+f"(d[19]),"+f"(d[20]),"+f"(d[21]),"+f"(d[22]),"+f"(d[23]),"+f"(d[24]),"+f"(d[25]),"+f"(d[26]),"+f"(d[27]),"+f"(d[28]),"+f"(d[29]),"+f"(d[30]),"+f"(d[31]),"+f"(d[32]),"+f"(d[33]),"+f"(d[34]),"+f"(d[35]),"+f"(d[36]),"+f"(d[37]),"+f"(d[38]),"+f"(d[39]),"+f"(d[40]),"+f"(d[41]),"+f"(d[42]),"+f"(d[43]),"+f"(d[44]),"+f"(d[45]),"+f"(d[46]),"+f"(d[47]),"+f"(d[48]),"+f"(d[49]),"+f"(d[50]),"+f"(d[51]),"+f"(d[52]),"+f"(d[53]),"+f"(d[54]),"+f"(d[55])
    : "r"(a0), "r"(a1), "r"(a2), "r"(a3), "r"(db), "r"(sd), "n"((uint32_t)(CB >> 32)));
}

constexpr int DM = 448;
constexpr int NCTA = 128;
#define MAPPING 1
#define GRID 132
#define PINGPONG 0
#define WIN 6
#define WIN_END 25
#define UNR_B 1
#define UNR_C 1
constexpr int kB = UNR_B, kC = UNR_C;
#define PACE 1
#define PACE_END 6
#define MAP_S 4
constexpr int SPIN_LIMIT = 1 << 22;

constexpr uint32_t OFF_X = 0, OFF_Y = 114688, OFF_MISC = 229376, SMEM_BYTES = 232448;
constexpr uint32_t Y_VR = 0, Y_K = 28672, Y_KOWN = 57344, Y_VOWN = 71680, Y_Q = 86016;
constexpr uint32_t HALF = 57344;
constexpr uint32_t M_BAR = OFF_MISC;
constexpr uint32_t M_ST = OFF_MISC + 512;
constexpr uint32_t M_G = OFF_MISC + 2304;
constexpr uint32_t M_EPOCH = OFF_MISC + 3040;
enum { B_XFULL = 0, B_FULLK = 7, B_FULLV = 8, B_FULLQ, B_KRFULL, B_VRFULL, B_WOFULL, B_XCH, B_FULL = 16, B_MOD1 = 28, B_MOD2, B_WMFULL,
       B_EMPTY = 32, B_XFREE = B_EMPTY + 12, B_GEMV, B_PEER,
       B_PUB = 47,
       B_WMFREE = 56, B_HRDY, B_GFULL = B_HRDY + 3, B_DONE = 31 };

__device__ uint32_t g_ticket;
__device__ __align__(128) uint32_t g_mod[8 * 6 * DM];
__device__ __align__(128) uint32_t g_flag[144 * 128];
constexpr int RB_WORDS = 262144, RB_KV = 0, RB_O = 57344, RB_X1 = 86016, RB_H2 = 143360, RB_ST = 258048;
__device__ __align__(128) uint32_t g_act[18 * RB_WORDS];
__device__ __align__(128) uint32_t g_wd[56 * 4 * 1792];
#define PROFH(id)
#define PROFH1(id)
#define PROFC(id)

struct alignas(64) Params {
    CUtensorMap wm, xm, qkv, wo, ga, ua, gb, ub, gc, uc, dn;
    const bf16 *x, *c, *wqkv, *wmod, *wg, *wu, *wd, *wop;
    bf16* out;
    uint32_t* actb;
    uint32_t zero;
};

__device__ __forceinline__ void mbar_init(uint32_t bar, int cnt) { asm volatile("mbarrier.init.shared::cta.b64 [%0], %1;" ::"r"(bar), "r"(cnt) : "memory"); }
__device__ __forceinline__ void mbar_expect_tx(uint32_t bar, uint32_t bytes) { asm volatile("mbarrier.arrive.expect_tx.shared::cta.b64 _, [%0], %1;" ::"r"(bar), "r"(bytes) : "memory"); }
__device__ __forceinline__ void mbar_arrive(uint32_t bar) { asm volatile("mbarrier.arrive.shared::cta.b64 _, [%0];" ::"r"(bar) : "memory"); }
__device__ __forceinline__ void mbar_wait(uint32_t bar, uint32_t parity) {
    uint32_t ok; int n = 0;
    do {
        asm volatile("{\n.reg .pred p;\nmbarrier.try_wait.parity.shared::cta.b64 p, [%1], %2;\nselp.u32 %0, 1, 0, p;\n}" : "=r"(ok) : "r"(bar), "r"(parity) : "memory");
        if (++n > SPIN_LIMIT) __trap();
    } while (!ok);
}
__device__ __forceinline__ void mbar_wait_c(uint32_t bar, uint32_t parity) {
    asm volatile("{\n.reg .pred p;\nWL:\nmbarrier.try_wait.parity.shared::cta.b64 p, [%0], %1;\n@!p bra WL;\n}" ::"r"(bar), "r"(parity) : "memory");
}
__device__ __forceinline__ void mbar_wait_cluster(uint32_t bar, uint32_t parity) {
    uint32_t ok; int n = 0;
    do {
        asm volatile("{\n.reg .pred p;\nmbarrier.try_wait.parity.acquire.cluster.shared::cta.b64 p, [%1], %2;\nselp.u32 %0, 1, 0, p;\n}" : "=r"(ok) : "r"(bar), "r"(parity) : "memory");
        if (++n > SPIN_LIMIT) __trap();
    } while (!ok);
}
__device__ __forceinline__ void warp_arrive(uint32_t bar) {
    __syncwarp();
    asm volatile("{\n.reg .pred p;\nelect.sync _|p, 0xffffffff;\n@p mbarrier.arrive.shared::cta.b64 _, [%0];\n}" ::"r"(bar) : "memory");
}
__device__ __forceinline__ int opaque(int v) { return __shfl_sync(~0u, v, 0); }
__device__ __forceinline__ int fresh_tid() { int v; asm volatile("mov.u32 %0, %%tid.x;" : "=r"(v)); return v; }
__device__ __forceinline__ void bar_sync(int id, int n) { asm volatile("bar.sync %0, %1;" ::"r"(id), "r"(n) : "memory"); }
__device__ __forceinline__ void bar_arrive(int id, int n) { asm volatile("bar.arrive %0, %1;" ::"r"(id), "r"(n) : "memory"); }
__device__ __forceinline__ void fence_async_smem() { asm volatile("fence.proxy.async.shared::cta;" ::: "memory"); }
__device__ __forceinline__ void fence_async_global() { asm volatile("fence.proxy.async.global;" ::: "memory"); }
__device__ __forceinline__ void fence_gpu() { asm volatile("fence.release.gpu;" ::: "memory"); }
__device__ __forceinline__ void tma3(uint32_t dst, const CUtensorMap* m, int c0, int c1, int c2, uint32_t bar) {
    asm volatile("cp.async.bulk.tensor.3d.shared::cluster.global.mbarrier::complete_tx::bytes [%0], [%1, {%3, %4, %5}], [%2];"
                 ::"r"(dst), "l"(m), "r"(bar), "r"(c0), "r"(c1), "r"(c2) : "memory");
}
__device__ __forceinline__ void bulk_load(uint32_t dst, const void* src, uint32_t bytes, uint32_t bar) {
    asm volatile("cp.async.bulk.shared::cluster.global.mbarrier::complete_tx::bytes [%0], [%1], %2, [%3];" ::"r"(dst), "l"(src), "r"(bytes), "r"(bar) : "memory");
}
__device__ __forceinline__ void expect_e(uint32_t bar, uint32_t bytes) {
    asm volatile("{\n.reg .pred p;\nelect.sync _|p, 0xffffffff;\n@p mbarrier.arrive.expect_tx.shared::cta.b64 _, [%0], %1;\n}" ::"r"(bar), "r"(bytes) : "memory");
}
__device__ __forceinline__ void tma3_e(uint32_t dst, const CUtensorMap* m, int c0, int c1, int c2, uint32_t bar) {
    asm volatile("{\n.reg .pred p;\nelect.sync _|p, 0xffffffff;\n@p cp.async.bulk.tensor.3d.shared::cluster.global.mbarrier::complete_tx::bytes [%0], [%1, {%3, %4, %5}], [%2];\n}"
                 ::"r"(dst), "l"(m), "r"(bar), "r"(c0), "r"(c1), "r"(c2) : "memory");
}
__device__ __forceinline__ void bulk_e(uint32_t dst, const void* src, uint32_t bytes, uint32_t bar) {
    asm volatile("{\n.reg .pred p;\nelect.sync _|p, 0xffffffff;\n@p cp.async.bulk.shared::cluster.global.mbarrier::complete_tx::bytes [%0], [%1], %2, [%3];\n}"
                 ::"r"(dst), "l"(src), "r"(bytes), "r"(bar) : "memory");
}
__device__ __forceinline__ void init_e(uint32_t bar, int cnt) {
    asm volatile("{\n.reg .pred p;\nelect.sync _|p, 0xffffffff;\n@p mbarrier.init.shared::cta.b64 [%0], %1;\n}" ::"r"(bar), "r"(cnt) : "memory");
}
__device__ __forceinline__ void l2_prefetch_e(const void* src, uint32_t bytes) {
    asm volatile("{\n.reg .pred p;\nelect.sync _|p, 0xffffffff;\n@p cp.async.bulk.prefetch.L2.global [%0], %1;\n}" ::"l"(src), "r"(bytes) : "memory");
}
__device__ __forceinline__ uint32_t ld_relaxed(const uint32_t* p) { uint32_t v; asm volatile("ld.relaxed.gpu.global.u32 %0, [%1];" : "=r"(v) : "l"(p) : "memory"); return v; }
__device__ __forceinline__ void st_relaxed(uint32_t* p, uint32_t v) { asm volatile("st.relaxed.gpu.global.u32 [%0], %1;" ::"l"(p), "r"(v) : "memory"); }
__device__ __forceinline__ uint4 ld_relaxed4(const uint4* p) { uint4 v; asm volatile("ld.relaxed.gpu.global.v4.u32 {%0,%1,%2,%3}, [%4];" : "=r"(v.x), "=r"(v.y), "=r"(v.z), "=r"(v.w) : "l"(p) : "memory"); return v; }
__device__ __forceinline__ void st_relaxed4(uint4* p, uint4 v) { asm volatile("st.relaxed.gpu.global.v4.u32 [%0], {%1,%2,%3,%4};" ::"l"(p), "r"(v.x), "r"(v.y), "r"(v.z), "r"(v.w) : "memory"); }
__device__ __forceinline__ uint4 ldg_nc4(const void* p) { uint4 v; asm volatile("ld.global.nc.L1::no_allocate.v4.u32 {%0,%1,%2,%3}, [%4];" : "=r"(v.x), "=r"(v.y), "=r"(v.z), "=r"(v.w) : "l"(p)); return v; }
__device__ __forceinline__ uint32_t ldg_nc(const void* p) { uint32_t v; asm volatile("ld.global.nc.u32 %0, [%1];" : "=r"(v) : "l"(p)); return v; }
__device__ __forceinline__ uint32_t ld_acquire(const uint32_t* p) { uint32_t v; asm volatile("ld.acquire.gpu.global.u32 %0, [%1];" : "=r"(v) : "l"(p) : "memory"); return v; }
__device__ __forceinline__ uint4 lds4(uint32_t a) { uint4 v; asm volatile("ld.shared.v4.u32 {%0,%1,%2,%3}, [%4];" : "=r"(v.x), "=r"(v.y), "=r"(v.z), "=r"(v.w) : "r"(a) : "memory"); return v; }
__device__ __forceinline__ float2 lds2f(uint32_t a) { float2 v; asm volatile("ld.shared.v2.f32 {%0,%1}, [%2];" : "=f"(v.x), "=f"(v.y) : "r"(a) : "memory"); return v; }
__device__ __forceinline__ uint32_t lds1(uint32_t a) { uint32_t v; asm volatile("ld.shared.u32 %0, [%1];" : "=r"(v) : "r"(a) : "memory"); return v; }
__device__ __forceinline__ void sts4(uint32_t a, uint4 v) { asm volatile("st.shared.v4.u32 [%0], {%1,%2,%3,%4};" ::"r"(a), "r"(v.x), "r"(v.y), "r"(v.z), "r"(v.w) : "memory"); }
__device__ __forceinline__ void sts2(uint32_t a, uint32_t x, uint32_t y) { asm volatile("st.shared.v2.u32 [%0], {%1,%2};" ::"r"(a), "r"(x), "r"(y) : "memory"); }
__device__ __forceinline__ void sts1(uint32_t a, uint32_t v) { asm volatile("st.shared.u32 [%0], %1;" ::"r"(a), "r"(v) : "memory"); }
__device__ __forceinline__ void stsm4(uint32_t a, uint32_t r0, uint32_t r1, uint32_t r2, uint32_t r3) {
    asm volatile("stmatrix.sync.aligned.m8n8.x4.shared.b16 [%0], {%1,%2,%3,%4};" ::"r"(a), "r"(r0), "r"(r1), "r"(r2), "r"(r3));
}
__device__ __forceinline__ uint32_t pack2(float lo, float hi) { uint32_t r; asm("cvt.rn.bf16x2.f32 %0, %1, %2;" : "=r"(r) : "f"(hi), "f"(lo)); return r; }
__device__ __forceinline__ uint32_t pack2_relu(float lo, float hi) { uint32_t r; asm("cvt.rn.relu.bf16x2.f32 %0, %1, %2;" : "=r"(r) : "f"(hi), "f"(lo)); return r; }
__device__ __forceinline__ uint32_t hfma2(uint32_t a, uint32_t b, uint32_t c) { uint32_t r; asm("fma.rn.bf16x2 %0, %1, %2, %3;" : "=r"(r) : "r"(a), "r"(b), "r"(c)); return r; }
__device__ __forceinline__ uint32_t hmul2(uint32_t a, uint32_t b) { uint32_t r; asm("mul.rn.bf16x2 %0, %1, %2;" : "=r"(r) : "r"(a), "r"(b)); return r; }
__device__ __forceinline__ float bf_lo(uint32_t v) { return __uint_as_float(v << 16); }
__device__ __forceinline__ float bf_hi(uint32_t v) { return __uint_as_float(v & 0xFFFF0000u); }
__device__ __forceinline__ float bf_round(float v) { return bf_lo(pack2(v, 0.f)); }
__device__ __forceinline__ float ex2(float x) { float r; asm("ex2.approx.ftz.f32 %0, %1;" : "=f"(r) : "f"(x)); return r; }
__device__ __forceinline__ void mma16816(float* d, uint32_t a0, uint32_t a1, uint32_t a2, uint32_t a3, uint32_t b0, uint32_t b1) {
    asm("mma.sync.aligned.m16n8k16.row.col.f32.bf16.bf16.f32 {%0,%1,%2,%3}, {%4,%5,%6,%7}, {%8,%9}, {%0,%1,%2,%3};"
        : "+f"(d[0]), "+f"(d[1]), "+f"(d[2]), "+f"(d[3]) : "r"(a0), "r"(a1), "r"(a2), "r"(a3), "r"(b0), "r"(b1));
}
__device__ __forceinline__ void mma16816_first(float* d, uint32_t a0, uint32_t a1, uint32_t a2, uint32_t a3, uint32_t b0, uint32_t b1) {
    asm volatile("mma.sync.aligned.m16n8k16.row.col.f32.bf16.bf16.f32 {%0,%1,%2,%3}, {%4,%5,%6,%7}, {%8,%9}, {%10,%10,%10,%10};"
        : "=f"(d[0]), "=f"(d[1]), "=f"(d[2]), "=f"(d[3]) : "r"(a0), "r"(a1), "r"(a2), "r"(a3), "r"(b0), "r"(b1), "f"(0.f));
}
__device__ __forceinline__ void mma16816_v(float* d, uint32_t a0, uint32_t a1, uint32_t a2, uint32_t a3, uint32_t b0, uint32_t b1) {
    asm volatile("mma.sync.aligned.m16n8k16.row.col.f32.bf16.bf16.f32 {%0,%1,%2,%3}, {%4,%5,%6,%7}, {%8,%9}, {%0,%1,%2,%3};"
        : "+f"(d[0]), "+f"(d[1]), "+f"(d[2]), "+f"(d[3]) : "r"(a0), "r"(a1), "r"(a2), "r"(a3), "r"(b0), "r"(b1));
}
__device__ __forceinline__ void mma1688(float* d, uint32_t a0, uint32_t a1, uint32_t b0) {
    asm("mma.sync.aligned.m16n8k8.row.col.f32.bf16.bf16.f32 {%0,%1,%2,%3}, {%4,%5}, {%6}, {%0,%1,%2,%3};"
        : "+f"(d[0]), "+f"(d[1]), "+f"(d[2]), "+f"(d[3]) : "r"(a0), "r"(a1), "r"(b0));
}
__device__ __forceinline__ void ldsm4(uint32_t a, uint32_t* r) {
    asm volatile("ldmatrix.sync.aligned.m8n8.x4.shared.b16 {%0,%1,%2,%3}, [%4];" : "=r"(r[0]), "=r"(r[1]), "=r"(r[2]), "=r"(r[3]) : "r"(a));
}
__device__ __forceinline__ void ldsm4t(uint32_t a, uint32_t* r) {
    asm volatile("ldmatrix.sync.aligned.m8n8.x4.trans.shared.b16 {%0,%1,%2,%3}, [%4];" : "=r"(r[0]), "=r"(r[1]), "=r"(r[2]), "=r"(r[3]) : "r"(a));
}
__device__ __forceinline__ float rcp(float x) { float r; asm("rcp.approx.ftz.f32 %0, %1;" : "=f"(r) : "f"(x)); return r; }
__device__ __forceinline__ uint2 ld_relaxed2(const void* p) { uint2 v; asm volatile("ld.relaxed.gpu.global.v2.u32 {%0,%1}, [%2];" : "=r"(v.x), "=r"(v.y) : "l"(p) : "memory"); return v; }
__device__ __forceinline__ void st_relaxed2(void* p, uint32_t x, uint32_t y) { asm volatile("st.relaxed.gpu.global.v2.u32 [%0], {%1,%2};" ::"l"(p), "r"(max(x, 1u)), "r"(max(y, 1u)) : "memory"); }
__host__ __device__ constexpr uint64_t dconst(uint32_t lbo, uint32_t sbo, uint32_t swz) {
    return ((uint64_t)(lbo >> 4) << 16) | ((uint64_t)(sbo >> 4) << 32) | ((uint64_t)swz << 62);
}
__device__ __forceinline__ uint32_t mkdesc(uint32_t addr, uint64_t c) { return (uint32_t)c | ((addr & 0x3FFFF) >> 4); }
#define WG_FENCE() asm volatile("wgmma.fence.sync.aligned;" ::: "memory")
#define WG_COMMIT() asm volatile("wgmma.commit_group.sync.aligned;" ::: "memory")
#define WG_WAIT(n) asm volatile("wgmma.wait_group.sync.aligned %0;" ::"n"(n) : "memory")
template <int N> __device__ __forceinline__ void reg_fence(float* d) {
#pragma unroll
    for (int i = 0; i < N; i++) asm volatile("" : "+f"(d[i])::"memory");
}
template <int N> __device__ __forceinline__ void reg_def(float* d) {
#pragma unroll
    for (int i = 0; i < N; i++) asm volatile("" : "=f"(d[i]));
}
template <int N> __device__ __forceinline__ void reg_def(uint32_t* d) {
#pragma unroll
    for (int i = 0; i < N; i++) asm volatile("" : "=r"(d[i]));
}
__device__ __forceinline__ bool is_unset(uint4 v) { return min(min(v.x, v.y), min(v.z, v.w)) == 0u; }
__device__ __forceinline__ uint4 nz4(uint32_t a, uint32_t b, uint32_t c, uint32_t d) { return make_uint4(max(a, 1u), max(b, 1u), max(c, 1u), max(d, 1u)); }
__device__ __forceinline__ void wait_flags(const uint32_t* p, uint32_t target, uint32_t mask) {
    int n = 0;
    while (~__ballot_sync(~0u, (int)(ld_relaxed(p) - target) >= 0) & mask) { if (++n > SPIN_LIMIT) __trap(); }
    asm volatile("fence.acquire.gpu;" ::: "memory");
}
__device__ __forceinline__ float silu_bf(uint32_t cbits) {
    const float c = __uint_as_float(cbits << 16);
    return bf_round(__fdividef(c, 1.f + fminf(ex2(-1.4426950408889634f * c), 1e30f)));
}
__device__ __forceinline__ void gemv_part(uint32_t wmbuf, int npanel, int wp, int lane) {
    const uint32_t wa = wmbuf + wp * 512 + (8 * (lane >> 4) + (lane & 7)) * 32 + ((lane >> 3) & 1) * 16;
    uint2 B[4];
#pragma unroll
    for (int i = 0; i < 4; i++) { const float2 v = lds2f(wmbuf + 28672 + (wp + 8 * i) * 32 + (lane & 3) * 8); B[i] = make_uint2(__float_as_uint(v.x), __float_as_uint(v.y)); }
#pragma unroll 1
    for (int pn = 0; pn < npanel; pn++) {
        float d[4] = {};
        uint32_t A[16];
#pragma unroll
        for (int i = 0; i < 4; i++) ldsm4t(wa + pn * 14336 + (i < 3 || wp < 4 ? i : 0) * 4096, A + 4 * i);
#pragma unroll
        for (int i = 0; i < 4; i++) mma16816(d, A[4 * i], A[4 * i + 1], A[4 * i + 2], A[4 * i + 3], B[i].x, B[i].y);
        if ((lane & 3) == 0) {
            sts1(wmbuf + 29696 + (wp * 32 + pn * 16 + (lane >> 2)) * 4, __float_as_uint(d[0]));
            sts1(wmbuf + 29696 + (wp * 32 + pn * 16 + 8 + (lane >> 2)) * 4, __float_as_uint(d[2]));
        }
    }
}
__device__ __forceinline__ int pass_f(int fs, int ps) { return 224 * fs + ((fs & 1) ? (ps == 0 ? 96 : ps == 1 ? 32 : 0) : (ps == 0 ? 0 : ps == 1 ? 128 : 192)); }
__device__ __forceinline__ constexpr uint32_t slot_off(int l) { return l * 16384; }
__device__ __forceinline__ void x1_fix(uint32_t* x, const uint32_t* g) {
    do {
#pragma unroll
        for (int i = 0; i < 8; i++) x[i] = ld_relaxed(g + (i >> 1) * 256 + (i & 1) * 32);
    } while (__any_sync(~0u, min(min(min(x[0], x[1]), min(x[2], x[3])), min(min(x[4], x[5]), min(x[6], x[7]))) == 0u));
}
__device__ __forceinline__ void ln_coeffs(float mean, float msq, uint32_t& r2, uint32_t& n2) {
    const float rs = bf_round(rsqrtf(fmaxf(msq - mean * mean, 0.f) + 1e-5f));
    r2 = pack2(rs, rs);
    n2 = pack2(-mean * rs, -mean * rs);
}

#define LOADW bulk_e(dst, g_wd + (size_t)((f >> 5) * 4 + nq) * 1792, 7168, bar);
template <int sec> __device__ __forceinline__ void ring_loader(const Params& p, uint32_t sb_, int r_, int j_, int lane) {
    const uint32_t sb = opaque(sb_);
    const int r = opaque(r_), j = opaque(j_), nq = j >> 1, fs = 4 * (j & 1) + nq;
    const int fa = pass_f(fs, 0), fb = pass_f(fs, 1), fc = pass_f(fs, 2);
#define BAR(i) (sb + M_BAR + 8 * (i))
#define kh (j & 1)
            int sl = 0;
            mbar_wait(BAR(B_PUB + 2), 0);
            wait_flags(g_flag + (8 * r + j) * 128 + 96 + lane, lds1(sb + M_EPOCH) + 1, 0xFFFFu);
            fence_async_global();
#pragma unroll 1
            for (int s = 0; s < 28; s++) {
                if (s >= PACE && s < PACE_END) mbar_wait(BAR(B_FULL + s - PACE), 0);
                const int ps = s < 14 ? 0 : s < 21 ? 1 : 2;
                const uint32_t half = ps < 2 ? 8192 : 4096;
                mbar_wait(BAR(B_EMPTY + sl), (s >= 7 && s < 14) || s >= 21);
                expect_e(BAR(B_FULL + sl), half);
                tma3_e(sb + slot_off(sl) + sec * half, &p.ga + 2 * ps + sec, 0, ps ? 64 * sl : 32 * s, ps == 0 ? fa >> 6 : ps == 1 ? fb >> 6 : fc >> 5, BAR(B_FULL + sl));
                sl = sl == 6 ? 0 : sl + 1;
            }
            if (!sec) PROFH(3);
#pragma unroll 1
            for (int e = 0; e < 4; e++) {
                const uint32_t dst = sb + slot_off(e) + sec * 8192, bar = BAR(B_FULL + e);
                const int f = (e < 2 ? fa + 64 * e : e == 2 ? fb : fc) + 32 * sec;
                mbar_wait(BAR(B_EMPTY + e), 0);
                expect_e(bar, e == 3 && sec ? 0 : 7168);
                if (!(e == 3 && sec)) { LOADW }
            }
            sl = 4;
            int e = 4;
#pragma unroll 1
            for (int grp = 0; grp < 9; grp++) {
                const int ps = grp >= 6 ? 2 : grp >= 3 ? 1 : 0;
                int sidx = grp - 3 * ps;
                if (sec && sidx == 0) { mbar_wait(BAR(B_HRDY + ps), 0); fence_async_global(); }
                sidx += sidx >= nq;
                int f = pass_f(4 * kh + sidx, ps);
#pragma unroll 1
                for (int k = 4 >> ps; k > 0; k--, e++, f += 32) {
                    const uint32_t dst = sb + slot_off(sl), bar = BAR(B_FULL + sl);
                    mbar_wait(BAR(B_EMPTY + sl), e >= 12 && e < 24);
                    if (e < WIN_END && e >= WIN) mbar_wait(BAR(B_FULL + (sl >= WIN ? sl - WIN : sl + 12 - WIN)), e - WIN >= 12);
                    expect_e(bar, sec ? 8192 : 7168);
                    if (!sec) { LOADW }
                    else bulk_e(dst + 8192, p.actb + (size_t)r * RB_WORDS + RB_H2 + f * 64, 8192, bar);
                    sl = sl == 11 ? 0 : sl + 1;
                }
            }
            if (!sec) PROFH(4);
}

__global__ void __cluster_dims__(2, 1, 1) __launch_bounds__(384, 1) fused_block_kernel(const __grid_constant__ Params p) {
    extern __shared__ __align__(1024) unsigned char smem[];
    const uint32_t sb = (uint32_t)__cvta_generic_to_shared(smem);
    const int tid = threadIdx.x, lane = tid & 31, warp = __shfl_sync(~0u, tid >> 5, 0);
    const int m = blockIdx.x >> 1;
    int r, nq;
    {
        int g, i;
        if (m < MAP_S) { g = m < 4 ? 15 : 16; i = m & 3; }
        else if (m < MAP_S + 32) { g = (m - MAP_S) & 7; i = (m - MAP_S) >> 3; }
        else if (m < MAP_S + 60) { i = (m - MAP_S - 32) / 7; g = 8 + (m - MAP_S - 32) - 7 * i; }
        else { g = 16; i = m & 3; }
        r = g; nq = i;
    }
    const int j = opaque(2 * nq + (blockIdx.x & 1)), b = 8 * r + j, fs = 4 * kh + nq;
#define act (p.actb + (size_t)r * RB_WORDS)
    const uint32_t sc = r == 16;
    if (lane == 0 && warp < 9 && warp != 6 && warp != 7) {
        const int i0 = warp == 8 ? 0 : 8 + 8 * warp, cnt = warp == 0 || warp == 8 ? 1 : warp < 3 ? 2 : 8;
#pragma unroll
        for (int k = 0; k < 8; k++) if (i0 + k != B_WMFULL) mbar_init(BAR(i0 + k), cnt);
        asm volatile("fence.mbarrier_init.release.cluster;" ::: "memory");
        fence_async_smem();
    }

    if (warp < 8) {
        const int w = warp >> 2, wi = warp & 3;
#define COORDS const int t = fresh_tid() & 127, lane = t & 31, q = lane & 3, lr = lane >> 2, ra = 64 * w + 16 * wi + lr; \
        const uint32_t lx = (lane >> 4) ^ (lane & 7), mrow = (64 * w + 16 * wi + ((lane >> 3) & 1) * 8 + (lane & 7)) * 128; \
        (void)q; (void)lr; (void)ra; (void)lx; (void)mrow;
        const int sid = 2 * (j & 3) + w;
#define RUN(k) (!sc || sid == (k))
#define WAIT(i, par) mbar_wait_c(BAR(i), (par) | sc)
        constexpr uint64_t DB128 = dconst(4096, 1024, 1);
        bar_arrive(9, 384);
        bar_sync(0, 384);
        asm volatile("barrier.cluster.arrive.relaxed.aligned;" ::: "memory");
        asm volatile("setmaxnreg.inc.sync.aligned.u32 224;");
        PROFC(0);
        uint32_t xr[16];
        {
            COORDS
            uint32_t h[112];
            if (RUN(0)) {
                float ds[4] = {}, da[2][4] = {}, db[2][4] = {};
                const uint32_t ONE2 = 0x3F803F80u;
                if (kh == 0) { WAIT(B_WMFULL, 0); gemv_part(sb + OFF_Y + HALF, 1, warp, lane); warp_arrive(BAR(B_GEMV)); }
#pragma unroll
                for (int kb = 0; kb < 7; kb++) {
                    WAIT(B_XFULL + kb, 0);
#pragma unroll
                    for (int k4 = 0; k4 < 4; k4++) ldsm4(sb + OFF_X + mrow + kb * 16384 + (((2 * k4) ^ lx) << 4), h + 16 * kb + 4 * k4);
#pragma unroll
                    for (int k4 = 0; k4 < 4; k4++) {
                        const uint32_t* f = h + 16 * kb + 4 * k4;
                        mma16816(ds, f[0], f[1], f[2], f[3], ONE2, ONE2);
                        mma1688(da[0], f[0], f[1], f[0]); mma1688(db[0], f[0], f[1], f[1]);
                        mma1688(da[1], f[2], f[3], f[2]); mma1688(db[1], f[2], f[3], f[3]);
                    }
                }
#pragma unroll
                for (int i = 0; i < 4; i++) {
                    const int ch = 7 * j + 2 * i + (lane >> 4);
                    ldsm4(sb + OFF_X + mrow + (ch >> 3) * 16384 + (((ch ^ lane) & 7) << 4), xr + 4 * i);
                }
                warp_arrive(BAR(B_XFREE));
                float qa = (lr & 1) ? da[0][1] + da[1][1] : da[0][0] + da[1][0];
                float qb = (lr & 1) ? db[0][3] + db[1][3] : db[0][2] + db[1][2];
                const int src = (lane & ~3) | (lr >> 1);
                qa = __shfl_sync(~0u, qa, src);
                qb = __shfl_sync(~0u, qb, src);
                uint32_t ra2, na2, rb2, nb2;
                ln_coeffs(ds[0] * (1.f / DM), qa * (1.f / DM), ra2, na2);
                ln_coeffs(ds[2] * (1.f / DM), qb * (1.f / DM), rb2, nb2);
#pragma unroll
                for (int i = 0; i < 112; i += 2) { h[i] = hfma2(h[i], ra2, na2); h[i + 1] = hfma2(h[i + 1], rb2, nb2); }
                if (kh == 1) { WAIT(B_WMFULL, 0); gemv_part(sb + OFF_Y + HALF, 2, warp, lane); warp_arrive(BAR(B_GEMV)); }
            } else { reg_def<112>(h); reg_def<16>(xr); }
            PROFC(1);
            if (RUN(1)) {
                float ak[28], av[28], aq[28];
                uint32_t kp[14], vp[14];
                const uint32_t bk0 = mkdesc(sb + OFF_Y, DB128) + kh, bv0 = mkdesc(sb + OFF_Y + HALF, DB128) + kh, bq0 = mkdesc(sb + OFF_X, DB128) + kh;
                uint32_t* kvg = act + RB_KV + j * 7168 + (8 * w + 2 * wi) * 224 + lane;
                WAIT(B_FULLK, 0);
                WAIT(B_MOD1, 0);
                PROFC(2);
                reg_def<28>(ak);
#pragma unroll
                for (int g4 = 0; g4 < 4; g4++) {
#pragma unroll
                    for (int ks = 7 * g4; ks < 7 * g4 + 7; ks++) {
                        const uint4 st = *(const uint4*)(smem + M_ST + ks * 64 + q * 16);
                        h[4 * ks] = hfma2(h[4 * ks], st.x, st.y); h[4 * ks + 1] = hfma2(h[4 * ks + 1], st.x, st.y);
                        h[4 * ks + 2] = hfma2(h[4 * ks + 2], st.z, st.w); h[4 * ks + 3] = hfma2(h[4 * ks + 3], st.z, st.w);
                    }
                    WG_FENCE();
#pragma unroll
                    for (int ks = 7 * g4; ks < 7 * g4 + 7; ks++) wgmma_rs_56<DB128>(ak, h[4 * ks], h[4 * ks + 1], h[4 * ks + 2], h[4 * ks + 3], bk0 + ks * 128, ks != 0);
                }
                WG_COMMIT();
                PROFC(3);
                WAIT(B_FULLV, 0);
                reg_def<28>(av);
                WG_FENCE();
#pragma unroll
                for (int ks = 0; ks < 8; ks++) wgmma_rs_56<DB128>(av, h[4 * ks], h[4 * ks + 1], h[4 * ks + 2], h[4 * ks + 3], bv0 + ks * 128, ks != 0);
                WG_COMMIT();
                WG_WAIT(1);
                reg_fence<28>(ak);
#pragma unroll
                for (int g = 0; g < 7; g++) {
                    kp[2 * g] = pack2(ak[4 * g], ak[4 * g + 1]); kp[2 * g + 1] = pack2(ak[4 * g + 2], ak[4 * g + 3]);
                    kvg[g * 32] = kp[2 * g]; kvg[224 + g * 32] = kp[2 * g + 1];
                }
                warp_arrive(BAR(B_PUB));
                PROFC(4);
                WG_FENCE();
#pragma unroll
                for (int ks = 8; ks < 28; ks++) wgmma_rs_56<DB128>(av, h[4 * ks], h[4 * ks + 1], h[4 * ks + 2], h[4 * ks + 3], bv0 + ks * 128, 1);
                WG_COMMIT();
                WAIT(B_FULLQ, 0);
                reg_def<28>(aq);
                WG_FENCE();
#pragma unroll
                for (int ks = 0; ks < 8; ks++) wgmma_rs_56<DB128>(aq, h[4 * ks], h[4 * ks + 1], h[4 * ks + 2], h[4 * ks + 3], bq0 + ks * 128, ks != 0);
                WG_COMMIT();
                WG_WAIT(1);
                reg_fence<28>(av);
#pragma unroll
                for (int g = 0; g < 7; g++) {
                    vp[2 * g] = pack2(av[4 * g], av[4 * g + 1]); vp[2 * g + 1] = pack2(av[4 * g + 2], av[4 * g + 3]);
                    kvg[3584 + g * 32] = vp[2 * g]; kvg[3584 + 224 + g * 32] = vp[2 * g + 1];
                }
                warp_arrive(BAR(B_PUB + 1));
                PROFC(5);
                WG_FENCE();
#pragma unroll
                for (int ks = 8; ks < 28; ks++) wgmma_rs_56<DB128>(aq, h[4 * ks], h[4 * ks + 1], h[4 * ks + 2], h[4 * ks + 3], bq0 + ks * 128, 1);
                WG_COMMIT();
                WAIT(B_PUB + 1, 0);
                const uint32_t ko = sb + OFF_Y + Y_KOWN + (8 * w + 2 * wi) * 896 + lane * 4;
                const uint32_t qo = sb + OFF_Y + Y_Q + (8 * w + 2 * wi) * 1024 + lane * 4;
#pragma unroll
                for (int g = 0; g < 7; g++) {
                    sts1(ko + g * 128, kp[2 * g]); sts1(ko + 896 + g * 128, kp[2 * g + 1]);
                    sts1(ko + (Y_VOWN - Y_KOWN) + g * 128, vp[2 * g]); sts1(ko + (Y_VOWN - Y_KOWN) + 896 + g * 128, vp[2 * g + 1]);
                }
                WG_WAIT(0);
                reg_fence<28>(aq);
                __syncwarp();
                if (lane < 3 && w == 1) mbar_arrive(BAR(B_EMPTY + lane));
#pragma unroll
                for (int g = 0; g < 7; g++) {
                    const uint32_t q0 = pack2(aq[4 * g], aq[4 * g + 1]), q1 = pack2(aq[4 * g + 2], aq[4 * g + 3]);
                    if (g == 3) {
                        sts1(qo + 3 * 128, q < 2 ? q0 : 0u); sts1(qo + 1024 + 3 * 128, q < 2 ? q1 : 0u);
                        sts1(qo + 4 * 128, q < 2 ? 0u : q0); sts1(qo + 1024 + 4 * 128, q < 2 ? 0u : q1);
                    } else {
                        const int ch = g < 3 ? g : g + 1;
                        sts1(qo + ch * 128, q0); sts1(qo + 1024 + ch * 128, q1);
                    }
                }
                if (!sc) bar_sync(3, 256);
            }
        }
        PROFC(6);
        WAIT(B_KRFULL, 0);
        PROFC(7);
        if (RUN(2)) {
#pragma unroll 1
            for (int hf = sc; hf < 2; hf++) {
                COORDS
                float s[136];
                float na = 0.f, nb = 0.f;
                const float CS = 0.18898223650461361f * 1.4426950408889634f;
                const int kg0 = 8 * hf + 2 * wi;
                const int pmin = 16 - 8 * r - 4 * hf - wi;
                const float NEG = __int_as_float(0xFF800000);
                {
                    uint32_t F[8];
                    const uint32_t qa = sb + OFF_Y + Y_Q + (kg0 + ((lane >> 3) & 1)) * 1024 + (4 * w + (lane >> 4)) * 128 + (lane & 7) * 16;
                    ldsm4(qa, F); ldsm4(qa + 256, F + 4);
                    uint32_t ka = sb + OFF_Y + Y_K + kg0 * 896 + (3 * w + (lane >> 3)) * 128 + (lane & 7) * 16;
#pragma unroll
                    for (int g = 0; g < 34; g++) {
                        uint32_t B[4];
                        if (g >= 12 && g % 4 == 0) ka += __float_as_uint(s[4 * (g - 12)]) & p.zero;
                        ldsm4(ka + g * 896, B);
                        mma16816_first(s + 4 * g, F[0], F[1], F[2], F[3], B[0], B[1]);
                        mma16816_v(s + 4 * g, F[4], F[5], F[6], F[7], B[2], B[3]);
                    }
                    const bool c0 = 2 * q > lr, c1 = 2 * q + 1 > lr;
                    if (!c0) { s[0] = NEG; s[6] = NEG; }
                    if (!c1) { s[1] = NEG; s[7] = NEG; }
                    s[2] = NEG; s[3] = NEG;
                    if (c0) { s[128] = NEG; s[134] = NEG; }
                    if (c1) { s[129] = NEG; s[135] = NEG; }
                    s[132] = NEG; s[133] = NEG;
                    float ma = NEG, mb = NEG;
#pragma unroll
                    for (int pp = 0; pp < 17; pp++) {
                        const float* e = s + 8 * pp;
                        const float bias = pp < pmin ? NEG : 0.f;
                        ma = fmaxf(ma, fmaxf(fmaxf(e[0], e[1]), fmaxf(e[4], e[5])) + bias);
                        mb = fmaxf(mb, fmaxf(fmaxf(e[2], e[3]), fmaxf(e[6], e[7])) + bias);
                    }
                    ma = fmaxf(ma, __shfl_xor_sync(~0u, ma, 1)); mb = fmaxf(mb, __shfl_xor_sync(~0u, mb, 1));
                    ma = fmaxf(ma, __shfl_xor_sync(~0u, ma, 2)); mb = fmaxf(mb, __shfl_xor_sync(~0u, mb, 2));
                    na = -ma * CS; nb = -mb * CS;
                }
                PROFC(8 + 3 * hf);
                {
                    WAIT(B_VRFULL, 0);
                    float o[16] = {}, rs[4] = {};
                    uint32_t pk[2];
                    const uint32_t va = sb + OFF_Y + Y_VR + (kg0 + ((lane >> 3) & 1)) * 896 + (3 * w + (lane >> 4)) * 128 + (lane & 7) * 16;
#pragma unroll
                    for (int pp = 0; pp < 17; pp++) {
                        uint32_t B[8];
                        const uint32_t v = va + pp * 1792 + (pp == 16 || (pp >= 9 && kg0 + 2 * pp >= 32) ? Y_VOWN - 32 * 896 : 0);
                        ldsm4t(v, B); ldsm4t(v + 256, B + 4);
                        float e[8];
                        const float bias = __uint_as_float((pp < pmin ? 0xFF800000u : 0u) | ((pp < 2 ? B[0] : pk[pp & 1]) & p.zero));
#pragma unroll
                        for (int i = 0; i < 8; i++) e[i] = ex2(fmaf(s[8 * pp + i], CS, ((i & 2) ? nb : na) + bias));
                        const uint32_t p0 = pack2(e[0], e[1]), p1 = pack2(e[2], e[3]), p2 = pack2(e[4], e[5]), p3 = pack2(e[6], e[7]);
                        pk[pp & 1] = p3;
                        mma16816(rs, p0, p1, p2, p3, 0x3F803F80u, 0x3F803F80u);
#pragma unroll
                        for (int g = 0; g < 4; g++) mma16816(o + 4 * g, p0, p1, p2, p3, B[2 * g], B[2 * g + 1]);
                    }
                    PROFC(9 + 3 * hf);
                    const float ia = rcp(rs[0]), ib = rcp(rs[2]);
                    uint32_t* og = act + RB_O + hf * 14336 + (7 * j + 3 * w) * 256 + wi * 64 + lane;
#pragma unroll
                    for (int g = 0; g < 4; g++) {
                        if ((g == 3 - 3 * w) ? ((q >> 1) == w) : true) {
                            og[g * 256] = pack2(o[4 * g] * ia, o[4 * g + 1] * ia);
                            og[g * 256 + 32] = pack2(o[4 * g + 2] * ib, o[4 * g + 3] * ib);
                        }
                    }
                    warp_arrive(BAR(B_PUB + 2 + hf));
                    PROFC(10 + 3 * hf);
                }
            }
        }
        uint32_t x1p[14];
        COORDS
        constexpr uint64_t DT = dconst(1024, 128, 0);
        const int tile = opaque((lds1(sb + M_EPOCH) & 1) * 2 + w);
        if (RUN(4)) {
            float ac[28];
            const uint32_t ad = mkdesc(sb + (w ? OFF_Y + HALF : OFF_X), DT), bd = mkdesc(sb + OFF_X + HALF, DB128) + kh;
            WAIT(B_WOFULL, 0);
            WAIT(B_MOD2, 0);
            WAIT(B_GFULL + w, 0);
            PROFC(28);
            reg_def<28>(ac);
#pragma unroll 1
            for (int u = 0; u < 4; u++) {
                if (u == 2) WAIT(B_XFULL + 2 + w, 1);
                WG_FENCE();
#pragma unroll
                for (int i = 0; i < 7; i++) wgmma_ss_56<DT, DB128>(ac, ad + (7 * u + i) * 128, bd + (7 * u + i) * 128, (u | i) != 0);
            }
            WG_COMMIT();
            WG_WAIT(0);
            reg_fence<28>(ac);
            PROFC(14);
            __syncwarp();
            if (lane < 4) mbar_arrive(BAR(B_EMPTY + 3 + lane));
            if (lane < 3 && w == 0) mbar_arrive(BAR(B_EMPTY + lane));
            float s1a = 0.f, s2a = 0.f, s1b = 0.f, s2b = 0.f;
            uint32_t* xo = act + RB_X1 + tile * 14336 + 7 * j * 256 + wi * 64 + lane;
#pragma unroll
            for (int g = 0; g < 7; g++) {
                const float2 ga = *(const float2*)(smem + M_G + (8 * g + 2 * q) * 4);
                x1p[2 * g] = pack2(fmaf(ga.x, ac[4 * g], bf_lo(xr[2 * g])), fmaf(ga.y, ac[4 * g + 1], bf_hi(xr[2 * g])));
                x1p[2 * g + 1] = pack2(fmaf(ga.x, ac[4 * g + 2], bf_lo(xr[2 * g + 1])), fmaf(ga.y, ac[4 * g + 3], bf_hi(xr[2 * g + 1])));
                st_relaxed(xo + g * 256, max(x1p[2 * g], 1u)); st_relaxed(xo + g * 256 + 32, max(x1p[2 * g + 1], 1u));
                const float u0 = bf_lo(x1p[2 * g]), u1 = bf_hi(x1p[2 * g]), u2 = bf_lo(x1p[2 * g + 1]), u3 = bf_hi(x1p[2 * g + 1]);
                s1a += u0 + u1; s2a += u0 * u0 + u1 * u1; s1b += u2 + u3; s2b += u2 * u2 + u3 * u3;
            }
            float ka = (q & 1) ? s2a : s1a, kb2 = (q & 1) ? s2b : s1b;
            ka += __shfl_xor_sync(~0u, (q & 1) ? s1a : s2a, 1); kb2 += __shfl_xor_sync(~0u, (q & 1) ? s1b : s2b, 1);
            const float kk = ((q & 2) ? kb2 : ka) + __shfl_xor_sync(~0u, (q & 2) ? ka : kb2, 2);
            st_relaxed(act + RB_ST + ((tile * 8 + j) * 64 + 16 * wi + lr + 4 * (q & 2)) * 2 + (q & 1), max(__float_as_uint(kk), 1u));
            __syncwarp();
            if (lane < 2) mbar_arrive(BAR(B_PUB + 4 + w));
        } else reg_def<14>(x1p);
        PROFC(15);
        uint32_t h2a[32], h2b[24];
        {
            const int fa = pass_f(fs, 0), fb = pass_f(fs, 1), fc = pass_f(fs, 2);
            uint32_t* h2g = act + RB_H2 + (8 * w + 2 * wi) * 32 + lane;
            const uint32_t a0 = mkdesc(sb + OFF_Y + w * HALF, DT);
            if (RUN(3)) {
                uint32_t ra2, na2, rb2, nb2;
                {
                    const uint32_t* sg = act + RB_ST + ((tile * 8 + 2 * q) * 64 + 16 * wi + lr) * 2;
                    uint2 u[4];
                    do {
#pragma unroll
                        for (int i = 0; i < 4; i++) u[i] = ld_relaxed2(sg + (i >> 1) * 128 + (i & 1) * 16);
                    } while (__any_sync(~0u, min(min(min(u[0].x, u[0].y), min(u[1].x, u[1].y)), min(min(u[2].x, u[2].y), min(u[3].x, u[3].y))) == 0u) && !sc);
                    float v[4] = {__uint_as_float(u[0].x) + __uint_as_float(u[2].x), __uint_as_float(u[0].y) + __uint_as_float(u[2].y),
                                  __uint_as_float(u[1].x) + __uint_as_float(u[3].x), __uint_as_float(u[1].y) + __uint_as_float(u[3].y)};
#pragma unroll
                    for (int i = 0; i < 4; i++) { v[i] += __shfl_xor_sync(~0u, v[i], 1); v[i] += __shfl_xor_sync(~0u, v[i], 2); }
                    ln_coeffs(v[0] * (1.f / DM), v[1] * (1.f / DM), ra2, na2);
                    ln_coeffs(v[2] * (1.f / DM), v[3] * (1.f / DM), rb2, nb2);
                }
                WAIT(B_GFULL + 2 + w, 0);
                PROFC(16);
                const uint32_t ha = sb + OFF_Y + w * HALF + (lane >> 4) * 1024 + (2 * wi + ((lane >> 3) & 1)) * 128 + (lane & 7) * 16;
                const uint32_t sta = sb + M_ST + q * 16;
                const uint32_t* xg = act + RB_X1 + tile * 14336 + wi * 64 + lane;
                uint32_t x[8];
                uint4 st[2];
                uint32_t hl = ha, sl2 = sta;
                auto load = [&]() {
                    ldsm4(hl, x); ldsm4(hl + 2048, x + 4);
                    st[0] = lds4(sl2); st[1] = lds4(sl2 + 64);
                };
                auto prep = [&](uint32_t* f, uint32_t adv) {
                    if (__any_sync(~0u, min(min(min(x[0], x[1]), min(x[2], x[3])), min(min(x[4], x[5]), min(x[6], x[7]))) == 0u) && !sc) x1_fix(x, xg + ((hl - ha) >> 2));
#pragma unroll
                    for (int i = 0; i < 2; i++) {
                        f[4 * i] = hfma2(hfma2(x[4 * i], ra2, na2), st[i].x, st[i].y); f[4 * i + 1] = hfma2(hfma2(x[4 * i + 1], rb2, nb2), st[i].x, st[i].y);
                        f[4 * i + 2] = hfma2(hfma2(x[4 * i + 2], ra2, na2), st[i].z, st[i].w); f[4 * i + 3] = hfma2(hfma2(x[4 * i + 3], rb2, nb2), st[i].z, st[i].w);
                    }
                    stsm4(hl, f[0], f[1], f[2], f[3]); stsm4(hl + 2048, f[4], f[5], f[6], f[7]);
                    hl += adv; sl2 += 128;
                    load();
                };
                float ac[128];
                uint32_t fr[3][8];
                uint32_t bd = mkdesc(sb, DB128), fb_ = BAR(B_FULL), par = sc;
                reg_def<128>(ac);
                load();
                prep(fr[0], 4096);
                PROFC(17);
#pragma unroll 1
                for (int s3 = 0; s3 < 15; s3 += 3) {
                    if (s3 == 3) mbar_wait_c(BAR(B_XFULL + 4 + w), 1);
#pragma unroll
                    for (int e = 0; e < 3; e++) {
                        const int s = s3 + e;
                        if (e < 2 || s3 < 12) {
                            const uint32_t* f = fr[e];
                            mbar_wait_c(fb_, par);
                            WG_FENCE();
                            wgmma_rs_256<DB128>(ac, f[0], f[1], f[2], f[3], bd, s != 0);
                            wgmma_rs_256<DB128>(ac, f[4], f[5], f[6], f[7], bd + 128, 1);
                            WG_COMMIT();
                            if (s < 13) prep(fr[(e + 1) % 3], s < 12 ? 4096 : 0);
                            WG_WAIT(1);
                            if (s > 0) warp_arrive(s == 7 ? BAR(B_EMPTY + 6) : fb_ + 8 * (B_EMPTY - B_FULL - 1));
                            bd += 1024; fb_ += 8;
                            if (s == 6) { bd -= 7 * 1024; fb_ -= 56; par = 1; }
                        }
                    }
                }
                PROFC(18);
                fence_async_smem();
                WG_WAIT(0);
                reg_fence<128>(ac);
                warp_arrive(BAR(B_EMPTY + 6));
#pragma unroll
                for (int g = 0; g < 16; g++) {
                    h2a[2 * g] = hmul2(pack2_relu(ac[4 * g], ac[4 * g + 1]), pack2(ac[64 + 4 * g], ac[64 + 4 * g + 1]));
                    h2a[2 * g + 1] = hmul2(pack2_relu(ac[4 * g + 2], ac[4 * g + 3]), pack2(ac[64 + 4 * g + 2], ac[64 + 4 * g + 3]));
                    h2g[(fa / 8 + g) * 512] = h2a[2 * g]; h2g[(fa / 8 + g) * 512 + 32] = h2a[2 * g + 1];
                }
                warp_arrive(BAR(B_PUB + 6));
                bar_sync(1 + w, 128);
            } else reg_def<32>(h2a);
            PROFC(19);
            if (RUN(5)) {
                float ac[64];
                reg_def<64>(ac);
                const uint32_t bx = mkdesc(sb, dconst(8192, 1024, 1));
#pragma unroll kB
                for (int s = 0; s < 7; s++) {
                    WAIT(B_FULL + s, 0);
                    const uint32_t ad = a0 + s * 512, bd = bx + (slot_off(s) >> 4);
                    WG_FENCE();
#pragma unroll
                    for (int k = 0; k < 4; k++) wgmma_ss_128<DT, DB128>(ac, ad + k * 128, bd + k * 128, (s | k) != 0);
                    WG_COMMIT();
                    if (s > 0) { WG_WAIT(1); warp_arrive(BAR(B_EMPTY + s - 1)); }
                }
                WG_WAIT(0);
                reg_fence<64>(ac);
                warp_arrive(BAR(B_EMPTY + 6));
#pragma unroll
                for (int g = 0; g < 8; g++) {
                    h2b[2 * g] = hmul2(pack2_relu(ac[4 * g], ac[4 * g + 1]), pack2(ac[32 + 4 * g], ac[32 + 4 * g + 1]));
                    h2b[2 * g + 1] = hmul2(pack2_relu(ac[4 * g + 2], ac[4 * g + 3]), pack2(ac[32 + 4 * g + 2], ac[32 + 4 * g + 3]));
                    h2g[(fb / 8 + g) * 512] = h2b[2 * g]; h2g[(fb / 8 + g) * 512 + 32] = h2b[2 * g + 1];
                }
                warp_arrive(BAR(B_PUB + 7));
            } else reg_def<16>(h2b);
            PROFC(27);
            if (RUN(6)) {
                float ac[32];
                reg_def<32>(ac);
                const uint32_t bx = mkdesc(sb, dconst(4096, 512, 2));
#pragma unroll kC
                for (int s = 0; s < 7; s++) {
                    WAIT(B_FULL + s, 1);
                    const uint32_t ad = a0 + s * 512, bd = bx + (slot_off(s) >> 4);
                    WG_FENCE();
#pragma unroll
                    for (int k = 0; k < 4; k++) wgmma_ss_64<DT, dconst(4096, 512, 2)>(ac, ad + k * 128, bd + k * 64, (s | k) != 0);
                    WG_COMMIT();
                    if (s > 0) { WG_WAIT(1); warp_arrive(BAR(B_EMPTY + s - 1)); }
                }
                WG_WAIT(0);
                reg_fence<32>(ac);
                __syncwarp();
                if (lane < 6) mbar_arrive(BAR(B_EMPTY + 6 + lane));
                PROFC(20);
#pragma unroll
                for (int g = 0; g < 4; g++) {
                    h2b[16 + 2 * g] = hmul2(pack2_relu(ac[4 * g], ac[4 * g + 1]), pack2(ac[16 + 4 * g], ac[16 + 4 * g + 1]));
                    h2b[16 + 2 * g + 1] = hmul2(pack2_relu(ac[4 * g + 2], ac[4 * g + 3]), pack2(ac[16 + 4 * g + 2], ac[16 + 4 * g + 3]));
                    h2g[(fc / 8 + g) * 512] = h2b[16 + 2 * g]; h2g[(fc / 8 + g) * 512 + 32] = h2b[16 + 2 * g + 1];
                }
                warp_arrive(BAR(B_PUB + 8));
                asm volatile("barrier.cluster.wait.aligned;" ::: "memory");
                if (lane == 0 && !sc) {
                    uint32_t rb;
                    asm volatile("mapa.shared::cluster.u32 %0, %1, %2;" : "=r"(rb) : "r"(BAR(B_PEER)), "r"(kh ^ 1));
                    asm volatile("mbarrier.arrive.relaxed.cluster.shared::cluster.b64 _, [%0];" ::"r"(rb) : "memory");
                }
            } else reg_def<8>(h2b + 16);
        }
        PROFC(21);
        if (RUN(7)) {
            float ac[56];
            reg_def<56>(ac);
            constexpr uint64_t DAN = dconst(2048, 128, 0);
            constexpr uint64_t DW = dconst(128, 512, 0);
            const uint32_t bx = mkdesc(sb, DW);
#pragma unroll
            for (int e = 0; e < 4; e++) {
                WAIT(B_FULL + e, 0);
                const uint32_t bd = bx + (slot_off(e) >> 4);
                const uint32_t* hh = e < 2 ? h2a + 16 * e : h2b + 16 * (e - 2);
                WG_FENCE();
#pragma unroll
                for (int k = 0; k < (e < 3 ? 4 : 2); k++) wgmma_rs_112<DW>(ac, hh[4 * k], hh[4 * k + 1], hh[4 * k + 2], hh[4 * k + 3], bd + (k >> 1) * 512 + (k & 1) * 16, (e | k) != 0);
                WG_COMMIT();
                if (e > 0) { WG_WAIT(1); warp_arrive(BAR(B_EMPTY + e - 1)); }
            }
            PROFC(22);
            uint32_t ad = mkdesc(sb + 4 * 16384 + 8192 + w * 1024, DAN), bd = bx + 4 * 1024, fb_ = BAR(B_FULL + 4), eb_ = BAR(B_EMPTY + 3), par = sc;
#pragma unroll 1
            for (int e = 4; e < 25; e++) {
                mbar_wait_c(fb_, par);
                WG_FENCE();
                wgmma_ss_112<DAN, DW>(ac, ad, bd, 1);
                wgmma_ss_112<DAN, DW>(ac, ad + 256, bd + 16, 1);
                WG_COMMIT();
                WG_WAIT(1);
                warp_arrive(eb_);
                eb_ = fb_ + 8 * (B_EMPTY - B_FULL);
                ad += 1024; bd += 1024; fb_ += 8;
                if (e == 11 || e == 23) { ad -= 12 * 1024; bd -= 12 * 1024; fb_ -= 96; par = (par ^ 1) | sc; }
            }
            mbar_wait_cluster(BAR(B_PEER), sc);
            WG_WAIT(0);
            reg_fence<56>(ac);
            PROFC(24);
            uint32_t rdst, rbar;
            asm volatile("mapa.shared::cluster.u32 %0, %1, %2;" : "=r"(rdst) : "r"(sb + OFF_Y + (5 + w) * 16384 + t * 16), "r"(kh ^ 1 ^ sc));
            asm volatile("mapa.shared::cluster.u32 %0, %1, %2;" : "=r"(rbar) : "r"(BAR(B_XCH + w)), "r"(kh ^ 1 ^ sc));
#define ACG(g, i) ac[4 * (g) + (i)]
#pragma unroll
            for (int g = 0; g < 7; g++) {
                const float v0 = kh ? ACG(g, 0) : ACG(g + 7, 0), v1 = kh ? ACG(g, 1) : ACG(g + 7, 1);
                const float v2 = kh ? ACG(g, 2) : ACG(g + 7, 2), v3 = kh ? ACG(g, 3) : ACG(g + 7, 3);
                if (!sc) asm volatile("st.async.shared::cluster.mbarrier::complete_tx::bytes.v4.f32 [%0], {%1,%2,%3,%4}, [%5];"
                             ::"r"(rdst + g * 2048), "f"(v0), "f"(v1), "f"(v2), "f"(v3), "r"(rbar) : "memory");
            }
            mbar_wait_cluster(BAR(B_XCH + w), sc);
            PROFC(25);
            bf16* og = (sc ? (bf16*)act : p.out + (size_t)128 * r * DM) + (size_t)ra * DM + 56 * j + 2 * q;
#pragma unroll
            for (int g = 0; g < 7; g++) {
                const uint4 rv = *(const uint4*)(smem + OFF_Y + (5 + w) * 16384 + t * 16 + g * 2048);
                const float2 gb = *(const float2*)(smem + M_G + 224 + (8 * g + 2 * q) * 4);
                const float v0 = (kh ? ACG(g + 7, 0) : ACG(g, 0)) + __uint_as_float(rv.x), v1 = (kh ? ACG(g + 7, 1) : ACG(g, 1)) + __uint_as_float(rv.y);
                const float v2 = (kh ? ACG(g + 7, 2) : ACG(g, 2)) + __uint_as_float(rv.z), v3 = (kh ? ACG(g + 7, 3) : ACG(g, 3)) + __uint_as_float(rv.w);
                *(uint32_t*)(og + 8 * g) = pack2(fmaf(gb.x, v0, bf_lo(x1p[2 * g])), fmaf(gb.y, v1, bf_hi(x1p[2 * g])));
                *(uint32_t*)(og + 8 * DM + 8 * g) = pack2(fmaf(gb.x, v2, bf_lo(x1p[2 * g + 1])), fmaf(gb.y, v3, bf_hi(x1p[2 * g + 1])));
            }
        }
        PROFC(26);
        bar_sync(1 + w, 128);
        if (wi == 0) warp_arrive(BAR(B_DONE));
    } else {
        const int lane = fresh_tid() & 31;
        const bool early = kh == 0, gemv = r < 14;
        const int mcol = early ? 16 * (4 * r + nq) : 2 * DM + 32 * (4 * r + nq);
        const uint32_t wmbuf = sb + OFF_Y + HALF;
        asm volatile("setmaxnreg.dec.sync.aligned.u32 56;");
        if (warp == 9) {
#pragma unroll
            for (int i = 56; i < 64; i++) init_e(BAR(i), 1);
            fence_async_smem();
        }
        if (warp == 8) { init_e(BAR(B_WMFULL), 2); fence_async_smem(); }
        bar_arrive(0, 384);
        asm volatile("barrier.cluster.arrive.relaxed.aligned;" ::: "memory");
        uint32_t target = 0;
        if (warp == 8) {
            if (!sc) {
                expect_e(BAR(B_WMFULL), gemv ? 28672 >> early : 0);
                if (early && gemv) { tma3_e(wmbuf, &p.wm, mcol, 0, 0, BAR(B_WMFULL)); tma3_e(wmbuf + 7168, &p.wm, mcol, 224, 0, BAR(B_WMFULL)); }
#pragma unroll 1
                for (int kb = 0; kb < 7; kb++) {
                    expect_e(BAR(B_XFULL + kb), 16384);
                    tma3_e(sb + OFF_X + kb * 16384, &p.xm, 64 * kb, 128 * r, 0, BAR(B_XFULL + kb));
                }
            }
#pragma unroll 1
            for (int mt = 0; mt < 4; mt++) {
                if (mt == 1) {
                    if (!early && gemv) {
#pragma unroll 1
                        for (int k = 0; k < 4; k++) tma3_e(wmbuf + k * 7168, &p.wm, mcol + (k >> 1) * 16, (k & 1) * 224, 0, BAR(B_WMFULL));
                    }
                    bar_sync(9, 384);
                    if (sc) return;
                    mbar_wait(BAR(B_MOD1), 0);
                    mbar_wait(BAR(B_WMFREE), 0);
                }
                if (mt == 2) mbar_wait(BAR(B_XFREE), 0);
                if (mt == 3) mbar_wait(BAR(B_VRFULL), 0);
                const uint32_t bar = BAR(mt == 3 ? B_WOFULL : B_FULLK + mt), dst = sb + (mt < 2 ? OFF_Y : OFF_X) + (mt & 1) * HALF;
                const int c0 = (mt < 2 ? DM + DM * mt : 0) + 56 * j - 8 * kh;
                if (!sc) {
                    expect_e(bar, HALF);
                    tma3_e(dst, mt == 3 ? &p.wo : &p.qkv, c0, 0, 0, bar);
                    tma3_e(dst + HALF / 2, mt == 3 ? &p.wo : &p.qkv, c0, 224, 0, bar);
                }
            }
            expect_e(BAR(B_XCH), 14336);
            expect_e(BAR(B_XCH + 1), 14336);
        } else {
            if (warp == 10 && !sc) {
                l2_prefetch_e((const char*)p.wqkv + (size_t)b * 9408, 9408);
                if (lane == 0) sts1(sb + M_EPOCH, atomicAdd(&g_ticket, 1u) / NCTA);
            }
            if (warp == 11) {
#pragma unroll
                for (int i = 0; i < 8; i++) {
                    const int wd = lane + 32 * i;
                    const uint32_t cb = i < 7 ? __ldg((const uint32_t*)p.c + wd) : 0u;
                    sts1(wmbuf + 28672 + (wd >> 3) * 32 + (wd & 3) * 8 + (wd & 4), pack2(silu_bf(cb & 0xFFFFu), silu_bf(cb >> 16)));
                }
            }
            bar_sync(9, 384);
            if (sc) return;
            target = lds1(sb + M_EPOCH) + 1;
            const uint32_t tag = target & 0xFFFFu;
            if (warp == 11) {
                warp_arrive(BAR(B_WMFULL));
                mbar_wait(BAR(B_GEMV), 0);
                float sum = 0.f;
#pragma unroll
                for (int i = 0; i < 8; i++) sum += *(const float*)(smem + OFF_Y + HALF + 29696 + (i * 32 + (early ? lane & 15 : lane)) * 4);
                const uint32_t word = (pack2(sum, 0.f) << 16) | tag;
                if (gemv) {
                    uint32_t* mg = g_mod + mcol + (early ? (lane & 15) + (lane >> 4) * 4 * 6 * DM : lane);
#pragma unroll
                    for (int i = 0; i < 8; i++) if (i < 4 || !early) st_relaxed(mg + i * 6 * DM, word);
                }
                warp_arrive(BAR(B_WMFREE));
            }
            const uint4* modp = (const uint4*)g_mod + (r & 7) * (6 * DM / 4);
            const bool p2 = warp == 11;
            mbar_wait(BAR(p2 ? B_PUB : B_XFULL + 4), 0);
#pragma unroll 1
            for (int it = p2 ? 0 : warp - 9; it < (p2 ? 2 : warp - 8); it++) {
                const int i0 = lane + 32 * it, imax = p2 ? 251 : 223;
                uint4 v[4];
#pragma unroll 1
                for (int n = 0;; n++) {
                    uint32_t bad = 0;
#pragma unroll
                    for (int k = 0; k < 4; k++) {
                        const int i = min(i0 + 64 * k, imax);
                        v[k] = ld_relaxed4(modp + (i < 224 ? (p2 ? 336 : 0) + i : (i < 238 ? 14 * j + i : 14 * j + i + 322)));
                        bad |= (v[k].x ^ tag) | (v[k].y ^ tag) | (v[k].z ^ tag) | (v[k].w ^ tag);
                    }
                    if (!__any_sync(~0u, bad & 0xFFFFu)) break;
                    if (n > SPIN_LIMIT) __trap();
                }
#pragma unroll
                for (int k = 0; k < 4; k++) {
                    const int i = min(i0 + 64 * k, imax);
                    if (i < 224) {
                        const int isc = i >= 112, c4 = i - 112 * isc;
                        const float one = isc ? 1.f : 0.f;
                        const uint32_t a = sb + M_ST + (c4 >> 2) * 64 + (c4 & 1) * 32 + (c4 & 2) * 4 + (isc ? 0 : 4);
                        sts1(a, pack2(bf_hi(v[k].x) + one, bf_hi(v[k].y) + one));
                        sts1(a + 16, pack2(bf_hi(v[k].z) + one, bf_hi(v[k].w) + one));
                    } else {
                        sts4(sb + M_G + (i - 224) * 16, make_uint4(v[k].x & 0xFFFF0000u, v[k].y & 0xFFFF0000u, v[k].z & 0xFFFF0000u, v[k].w & 0xFFFF0000u));
                    }
                }
                warp_arrive(BAR(p2 ? B_MOD2 : B_MOD1));
            }
            if (warp == 9) {
#pragma unroll 1
                for (int kv = 0; kv < 2; kv++) {
                    mbar_wait(BAR(B_PUB + kv), 0);
                    wait_flags(g_flag + b * 128 + lane, target, (r >= 2 ? 6u : r == 1 ? 2u : 0u) << (8 * kv));
                    fence_async_global();
                    const uint32_t dst = sb + OFF_Y + (kv ? Y_VR : Y_K);
                    expect_e(BAR(B_KRFULL + kv), r >= 2 ? 28672 : r == 1 ? 14336 : 0);
                    if (r >= 2) bulk_e(dst, act - 2 * RB_WORDS + RB_KV + j * 7168 + kv * 3584, 14336, BAR(B_KRFULL + kv));
                    if (r >= 1) bulk_e(dst + 14336, act - RB_WORDS + RB_KV + j * 7168 + kv * 3584, 14336, BAR(B_KRFULL + kv));
                }
            } else if (warp == 11) {
                mbar_wait(BAR(B_VRFULL), 0);
                l2_prefetch_e((const char*)p.wg + (size_t)b * 12544, 12544);
                l2_prefetch_e((const char*)p.wu + (size_t)b * 12544, 12544);
#pragma unroll 1
                for (int k = 0; k < (r < 12 ? 2 : 1); k++) {
                    const int u = 28 * kh + r + 16 * k;
                    expect_e(BAR(B_XFULL + k), 7168);
                    tma3_e(sb + OFF_Y + 102400, &p.dn, 0, 32 * u, 14 * nq, BAR(B_XFULL + k));
                    mbar_wait(BAR(B_XFULL + k), 1);
                    asm volatile("{\n.reg .pred p;\nelect.sync _|p, 0xffffffff;\n@p cp.async.bulk.global.shared::cta.bulk_group [%0], [%1], 7168;\n"
                                 "cp.async.bulk.commit_group;\ncp.async.bulk.wait_group 0;\n}" ::"l"(g_wd + (size_t)(u * 4 + nq) * 1792), "r"(sb + OFF_Y + 102400) : "memory");
                    __syncwarp();
                }
                warp_arrive(BAR(B_WMFREE));
                fence_gpu();
                if (lane < 16) st_relaxed(g_flag + (8 * lane + j) * 128 + 96 + r, target);
            }
        }
        if (warp == 8 || warp == 11) {
            const int sec = warp == 11;
            if (sec) ring_loader<1>(p, sb, r, j, lane); else ring_loader<0>(p, sb, r, j, lane);
            mbar_wait(BAR(B_DONE), 0);
        } else if (warp == 9) {
#pragma unroll
            for (int ev = 0; ev < 4; ev++) { expect_e(BAR(B_GFULL + ev), ev < 2 ? HALF / 2 : 20480); expect_e(BAR(B_XFULL + 2 + ev), ev < 2 ? HALF / 2 : HALF - 20480); }
            mbar_wait(BAR(B_PUB + 2), 0);
            const uint32_t* fp = g_flag + b * 128 + 32 + lane;
            const int par = (target - 1) & 1;
#pragma unroll 1
            for (int n = 0, ev = 0; ev < 4; n++) {
                if (ev == 1) { mbar_wait(BAR(B_WMFREE), 1); mbar_wait(BAR(B_PUB + 3), 0); }
                uint32_t ok = __ballot_sync(~0u, (int)(ld_relaxed(fp) - target) >= 0) >> (8 * ev);
                while ((ok & 0xFFu) == 0xFFu) {
                    asm volatile("fence.acquire.gpu;" ::: "memory");
                    fence_async_global();
                    const int tile = (ev & 1) + (ev >> 1) * par * 2;
                    const uint32_t dst = sb + (ev == 0 ? OFF_X : OFF_Y + (ev & 1) * HALF), first = ev < 2 ? HALF / 2 : 20480;
                    const char* src = (const char*)(act + RB_O + ((ev >> 1) * 2 + tile) * 14336);
                    bulk_e(dst, src, first, BAR(B_GFULL + ev));
                    bulk_e(dst + first, src + first, HALF - first, BAR(B_XFULL + 2 + ev));
                    if (ev) PROFH(4 + ev);
                    ev++; ok >>= 8;
                }
                if (n > SPIN_LIMIT) __trap();
            }
            mbar_wait(BAR(B_XFULL + 5), 1);
#pragma unroll 1
            for (int hf = 0; hf < 2; hf++) {
                const int tile = (par ^ 1) * 2 + hf;
                uint4* xz = (uint4*)(act + RB_X1 + tile * 14336 + j * 1792) + lane;
#pragma unroll
                for (int i = 0; i < 14; i++) xz[i * 32] = make_uint4(0, 0, 0, 0);
                ((uint4*)(act + RB_ST + (tile * 8 + j) * 128))[lane] = make_uint4(0, 0, 0, 0);
            }
#pragma unroll 1
            for (int ps = 0; ps < 3; ps++) {
                mbar_wait(BAR(B_PUB + 6 + ps), 0);
                wait_flags(g_flag + b * 128 + 64 + lane, target, (0x55u << kh) << (8 * ps));
                warp_arrive(BAR(B_HRDY + ps));
                PROFH(9 + ps);
            }
        } else {
#pragma unroll 1
            for (int k = 0; k < 9; k++) {
                uint32_t* fp = k < 2 ? g_flag + (b + 8 * lane) * 128 + k * 8 + lane : g_flag + (8 * r + lane) * 128 + 16 + k * 8 + j;
                mbar_wait(BAR(B_PUB + k), 0);
                if (k != 4 && k != 5) fence_gpu();
                if (k < 2 ? (lane == 1 || lane == 2) : lane < 8) st_relaxed(fp, target);
                if (k >= 3 && k <= 5) PROFH(k - 3);
            }
        }
    }
}

#undef act
typedef CUresult (*EncodeFn)(CUtensorMap*, CUtensorMapDataType, cuuint32_t, void*, const cuuint64_t*, const cuuint64_t*, const cuuint32_t*,
                             const cuuint32_t*, CUtensorMapInterleave, CUtensorMapSwizzle, CUtensorMapL2promotion, CUtensorMapFloatOOBfill);

static void make_map(EncodeFn fn, CUtensorMap* m, const void* ptr, uint64_t d0, uint64_t d1, uint64_t d2, uint64_t s1, uint64_t s2,
                     uint32_t b0, uint32_t b1, uint32_t b2, CUtensorMapSwizzle sw) {
    cuuint64_t dims[3] = {d0, d1, d2}, strides[2] = {s1, s2};
    cuuint32_t box[3] = {b0, b1, b2}, es[3] = {1, 1, 1};
    CUresult rc = fn(m, CU_TENSOR_MAP_DATA_TYPE_BFLOAT16, 3, (void*)ptr, dims, strides, box, es, CU_TENSOR_MAP_INTERLEAVE_NONE, sw,
                     CU_TENSOR_MAP_L2_PROMOTION_L2_128B, CU_TENSOR_MAP_FLOAT_OOB_FILL_NONE);
    (void)rc;
}

extern "C" void kernel_launch(void* const* d_in, const int* in_sizes, int n_in, void* d_out, int out_size) {
    (void)in_sizes; (void)n_in; (void)out_size;
    static EncodeFn fn = nullptr;
    static uint32_t* act_base = nullptr;
    if (!fn) {
        cudaDriverEntryPointQueryResult st;
        cudaGetDriverEntryPoint("cuTensorMapEncodeTiled", (void**)&fn, cudaEnableDefault, &st);
        void* a = nullptr;
        cudaGetSymbolAddress(&a, g_act);
        act_base = (uint32_t*)(((uintptr_t)a + 0xFFFFF) & ~(uintptr_t)0xFFFFF);
        cudaFuncSetAttribute(fused_block_kernel, cudaFuncAttributeMaxDynamicSharedMemorySize, SMEM_BYTES);
    }
    Params p;
    p.x = (const bf16*)d_in[0];
    const bf16* wqkv = (const bf16*)d_in[1];
    p.wqkv = wqkv;
    p.wop = (const bf16*)d_in[2];
    p.wg = (const bf16*)d_in[4];
    p.wu = (const bf16*)d_in[5];
    p.wd = (const bf16*)d_in[6];
    p.c = (const bf16*)d_in[7];
    p.wmod = (const bf16*)d_in[8];
    p.out = (bf16*)d_out;
    p.zero = 0;
    p.actb = act_base;
    make_map(fn, &p.wm, p.wmod, 2688, 448, 1, 5376, 5376 * 448, 16, 224, 1, CU_TENSOR_MAP_SWIZZLE_NONE);
    make_map(fn, &p.xm, p.x, 448, 2048, 1, 896, 896 * 2048, 64, 128, 1, CU_TENSOR_MAP_SWIZZLE_128B);
    make_map(fn, &p.qkv, wqkv, 1344, 448, 1, 2688, 2688 * 448, 64, 224, 1, CU_TENSOR_MAP_SWIZZLE_128B);
    make_map(fn, &p.wo, p.wop, 448, 448, 1, 896, 896 * 448, 64, 224, 1, CU_TENSOR_MAP_SWIZZLE_128B);
    make_map(fn, &p.ga, p.wg, 64, 448, 28, 3584, 128, 64, 32, 2, CU_TENSOR_MAP_SWIZZLE_128B);
    make_map(fn, &p.ua, p.wu, 64, 448, 28, 3584, 128, 64, 32, 2, CU_TENSOR_MAP_SWIZZLE_128B);
    make_map(fn, &p.gb, p.wg, 64, 448, 28, 3584, 128, 64, 64, 1, CU_TENSOR_MAP_SWIZZLE_128B);
    make_map(fn, &p.ub, p.wu, 64, 448, 28, 3584, 128, 64, 64, 1, CU_TENSOR_MAP_SWIZZLE_128B);
    make_map(fn, &p.gc, p.wg, 32, 448, 56, 3584, 64, 32, 64, 1, CU_TENSOR_MAP_SWIZZLE_64B);
    make_map(fn, &p.uc, p.wu, 32, 448, 56, 3584, 64, 32, 64, 1, CU_TENSOR_MAP_SWIZZLE_64B);
    make_map(fn, &p.dn, p.wd, 8, 1792, 56, 896, 16, 8, 32, 14, CU_TENSOR_MAP_SWIZZLE_NONE);
    fused_block_kernel<<<GRID, 384, SMEM_BYTES>>>(p);
}
```

```cpp
#include <cuda_runtime.h>
#include <cuda_bf16.h>
#include <cuda.h>
#include <stdint.h>

typedef __nv_bfloat16 bf16;

template<uint64_t CB> __device__ __forceinline__ void wgmma_rs_56(float* d, uint32_t a0, uint32_t a1, uint32_t a2, uint32_t a3, uint32_t db, int sd) {
  asm volatile("{\n.reg .pred p;\n.reg .b64 b;\nsetp.ne.b32 p, %33, 0;\nmov.b64 b, {%32, %34};\n"
    "wgmma.mma_async.sync.aligned.m64n56k16.f32.bf16.bf16 {%0,%1,%2,%3,%4,%5,%6,%7,%8,%9,%10,%11,%12,%13,%14,%15,%16,%17,%18,%19,%20,%21,%22,%23,%24,%25,%26,%27}, {%28,%29,%30,%31}, b, p, 1, 1, 1;\n}\n"
    : "+f"(d[0]),"+f"(d[1]),"+f"(d[2]),"+f"(d[3]),"+f"(d[4]),"+f"(d[5]),"+f"(d[6]),"+f"(d[7]),"+f"(d[8]),"+f"(d[9]),"+f"(d[10]),"+f"(d[11]),"+f"(d[12]),"+f"(d[13]),"+f"(d[14]),"+f"(d[15]),"+f"(d[16]),"+f"(d[17]),"+f"(d[18]),"+f"(d[19]),"+f"(d[20]),"+f"(d[21]),"+f"(d[22]),"+f"(d[23]),"+f"(d[24]),"+f"(d[25]),"+f"(d[26]),"+f"(d[27])
    : "r"(a0), "r"(a1), "r"(a2), "r"(a3), "r"(db), "r"(sd), "n"((uint32_t)(CB >> 32)));
}
template<uint64_t CA, uint64_t CB> __device__ __forceinline__ void wgmma_ss_56(float* d, uint32_t da, uint32_t db, int sd) {
  asm volatile("{\n.reg .pred p;\n.reg .b64 a, b;\nsetp.ne.b32 p, %30, 0;\nmov.b64 a, {%28, %31};\nmov.b64 b, {%29, %32};\n"
    "wgmma.mma_async.sync.aligned.m64n56k16.f32.bf16.bf16 {%0,%1,%2,%3,%4,%5,%6,%7,%8,%9,%10,%11,%12,%13,%14,%15,%16,%17,%18,%19,%20,%21,%22,%23,%24,%25,%26,%27}, a, b, p, 1, 1, 0, 1;\n}\n"
    : "+f"(d[0]),"+f"(d[1]),"+f"(d[2]),"+f"(d[3]),"+f"(d[4]),"+f"(d[5]),"+f"(d[6]),"+f"(d[7]),"+f"(d[8]),"+f"(d[9]),"+f"(d[10]),"+f"(d[11]),"+f"(d[12]),"+f"(d[13]),"+f"(d[14]),"+f"(d[15]),"+f"(d[16]),"+f"(d[17]),"+f"(d[18]),"+f"(d[19]),"+f"(d[20]),"+f"(d[21]),"+f"(d[22]),"+f"(d[23]),"+f"(d[24]),"+f"(d[25]),"+f"(d[26]),"+f"(d[27])
    : "r"(da), "r"(db), "r"(sd), "n"((uint32_t)(CA >> 32)), "n"((uint32_t)(CB >> 32)));
}
template<uint64_t CA, uint64_t CB> __device__ __forceinline__ void wgmma_ss_256(float* d, uint32_t da, uint32_t db, int sd) {
  asm volatile("{\n.reg .pred p;\n.reg .b64 a, b;\nsetp.ne.b32 p, %130, 0;\nmov.b64 a, {%128, %131};\nmov.b64 b, {%129, %132};\n"
    "wgmma.mma_async.sync.aligned.m64n256k16.f32.bf16.bf16 {%0,%1,%2,%3,%4,%5,%6,%7,%8,%9,%10,%11,%12,%13,%14,%15,%16,%17,%18,%19,%20,%21,%22,%23,%24,%25,%26,%27,%28,%29,%30,%31,%32,%33,%34,%35,%36,%37,%38,%39,%40,%41,%42,%43,%44,%45,%46,%47,%48,%49,%50,%51,%52,%53,%54,%55,%56,%57,%58,%59,%60,%61,%62,%63,%64,%65,%66,%67,%68,%69,%70,%71,%72,%73,%74,%75,%76,%77,%78,%79,%80,%81,%82,%83,%84,%85,%86,%87,%88,%89,%90,%91,%92,%93,%94,%95,%96,%97,%98,%99,%100,%101,%102,%103,%104,%105,%106,%107,%108,%109,%110,%111,%112,%113,%114,%115,%116,%117,%118,%119,%120,%121,%122,%123,%124,%125,%126,%127}, a, b, p, 1, 1, 0, 1;\n}\n"
    : "+f"(d[0]),"+f"(d[1]),"+f"(d[2]),"+f"(d[3]),"+f"(d[4]),"+f"(d[5]),"+f"(d[6]),"+f"(d[7]),"+f"(d[8]),"+f"(d[9]),"+f"(d[10]),"+f"(d[11]),"+f"(d[12]),"+f"(d[13]),"+f"(d[14]),"+f"(d[15]),"+f"(d[16]),"+f"(d[17]),"+f"(d[18]),"+f"(d[19]),"+f"(d[20]),"+f"(d[21]),"+f"(d[22]),"+f"(d[23]),"+f"(d[24]),"+f"(d[25]),"+f"(d[26]),"+f"(d[27]),"+f"(d[28]),"+f"(d[29]),"+f"(d[30]),"+f"(d[31]),"+f"(d[32]),"+f"(d[33]),"+f"(d[34]),"+f"(d[35]),"+f"(d[36]),"+f"(d[37]),"+f"(d[38]),"+f"(d[39]),"+f"(d[40]),"+f"(d[41]),"+f"(d[42]),"+f"(d[43]),"+f"(d[44]),"+f"(d[45]),"+f"(d[46]),"+f"(d[47]),"+f"(d[48]),"+f"(d[49]),"+f"(d[50]),"+f"(d[51]),"+f"(d[52]),"+f"(d[53]),"+f"(d[54]),"+f"(d[55]),"+f"(d[56]),"+f"(d[57]),"+f"(d[58]),"+f"(d[59]),"+f"(d[60]),"+f"(d[61]),"+f"(d[62]),"+f"(d[63]),"+f"(d[64]),"+f"(d[65]),"+f"(d[66]),"+f"(d[67]),"+f"(d[68]),"+f"(d[69]),"+f"(d[70]),"+f"(d[71]),"+f"(d[72]),"+f"(d[73]),"+f"(d[74]),"+f"(d[75]),"+f"(d[76]),"+f"(d[77]),"+f"(d[78]),"+f"(d[79]),"+f"(d[80]),"+f"(d[81]),"+f"(d[82]),"+f"(d[83]),"+f"(d[84]),"+f"(d[85]),"+f"(d[86]),"+f"(d[87]),"+f"(d[88]),"+f"(d[89]),"+f"(d[90]),"+f"(d[91]),"+f"(d[92]),"+f"(d[93]),"+f"(d[94]),"+f"(d[95]),"+f"(d[96]),"+f"(d[97]),"+f"(d[98]),"+f"(d[99]),"+f"(d[100]),"+f"(d[101]),"+f"(d[102]),"+f"(d[103]),"+f"(d[104]),"+f"(d[105]),"+f"(d[106]),"+f"(d[107]),"+f"(d[108]),"+f"(d[109]),"+f"(d[110]),"+f"(d[111]),"+f"(d[112]),"+f"(d[113]),"+f"(d[114]),"+f"(d[115]),"+f"(d[116]),"+f"(d[117]),"+f"(d[118]),"+f"(d[119]),"+f"(d[120]),"+f"(d[121]),"+f"(d[122]),"+f"(d[123]),"+f"(d[124]),"+f"(d[125]),"+f"(d[126]),"+f"(d[127])
    : "r"(da), "r"(db), "r"(sd), "n"((uint32_t)(CA >> 32)), "n"((uint32_t)(CB >> 32)));
}
template<uint64_t CA, uint64_t CB> __device__ __forceinline__ void wgmma_ss_128(float* d, uint32_t da, uint32_t db, int sd) {
  asm volatile("{\n.reg .pred p;\n.reg .b64 a, b;\nsetp.ne.b32 p, %66, 0;\nmov.b64 a, {%64, %67};\nmov.b64 b, {%65, %68};\n"
    "wgmma.mma_async.sync.aligned.m64n128k16.f32.bf16.bf16 {%0,%1,%2,%3,%4,%5,%6,%7,%8,%9,%10,%11,%12,%13,%14,%15,%16,%17,%18,%19,%20,%21,%22,%23,%24,%25,%26,%27,%28,%29,%30,%31,%32,%33,%34,%35,%36,%37,%38,%39,%40,%41,%42,%43,%44,%45,%46,%47,%48,%49,%50,%51,%52,%53,%54,%55,%56,%57,%58,%59,%60,%61,%62,%63}, a, b, p, 1, 1, 0, 1;\n}\n"
    : "+f"(d[0]),"+f"(d[1]),"+f"(d[2]),"+f"(d[3]),"+f"(d[4]),"+f"(d[5]),"+f"(d[6]),"+f"(d[7]),"+f"(d[8]),"+f"(d[9]),"+f"(d[10]),"+f"(d[11]),"+f"(d[12]),"+f"(d[13]),"+f"(d[14]),"+f"(d[15]),"+f"(d[16]),"+f"(d[17]),"+f"(d[18]),"+f"(d[19]),"+f"(d[20]),"+f"(d[21]),"+f"(d[22]),"+f"(d[23]),"+f"(d[24]),"+f"(d[25]),"+f"(d[26]),"+f"(d[27]),"+f"(d[28]),"+f"(d[29]),"+f"(d[30]),"+f"(d[31]),"+f"(d[32]),"+f"(d[33]),"+f"(d[34]),"+f"(d[35]),"+f"(d[36]),"+f"(d[37]),"+f"(d[38]),"+f"(d[39]),"+f"(d[40]),"+f"(d[41]),"+f"(d[42]),"+f"(d[43]),"+f"(d[44]),"+f"(d[45]),"+f"(d[46]),"+f"(d[47]),"+f"(d[48]),"+f"(d[49]),"+f"(d[50]),"+f"(d[51]),"+f"(d[52]),"+f"(d[53]),"+f"(d[54]),"+f"(d[55]),"+f"(d[56]),"+f"(d[57]),"+f"(d[58]),"+f"(d[59]),"+f"(d[60]),"+f"(d[61]),"+f"(d[62]),"+f"(d[63])
    : "r"(da), "r"(db), "r"(sd), "n"((uint32_t)(CA >> 32)), "n"((uint32_t)(CB >> 32)));
}
template<uint64_t CA, uint64_t CB> __device__ __forceinline__ void wgmma_ss_64(float* d, uint32_t da, uint32_t db, int sd) {
  asm volatile("{\n.reg .pred p;\n.reg .b64 a, b;\nsetp.ne.b32 p, %34, 0;\nmov.b64 a, {%32, %35};\nmov.b64 b, {%33, %36};\n"
    "wgmma.mma_async.sync.aligned.m64n64k16.f32.bf16.bf16 {%0,%1,%2,%3,%4,%5,%6,%7,%8,%9,%10,%11,%12,%13,%14,%15,%16,%17,%18,%19,%20,%21,%22,%23,%24,%25,%26,%27,%28,%29,%30,%31}, a, b, p, 1, 1, 0, 1;\n}\n"
    : "+f"(d[0]),"+f"(d[1]),"+f"(d[2]),"+f"(d[3]),"+f"(d[4]),"+f"(d[5]),"+f"(d[6]),"+f"(d[7]),"+f"(d[8]),"+f"(d[9]),"+f"(d[10]),"+f"(d[11]),"+f"(d[12]),"+f"(d[13]),"+f"(d[14]),"+f"(d[15]),"+f"(d[16]),"+f"(d[17]),"+f"(d[18]),"+f"(d[19]),"+f"(d[20]),"+f"(d[21]),"+f"(d[22]),"+f"(d[23]),"+f"(d[24]),"+f"(d[25]),"+f"(d[26]),"+f"(d[27]),"+f"(d[28]),"+f"(d[29]),"+f"(d[30]),"+f"(d[31])
    : "r"(da), "r"(db), "r"(sd), "n"((uint32_t)(CA >> 32)), "n"((uint32_t)(CB >> 32)));
}
template<uint64_t CA, uint64_t CB> __device__ __forceinline__ void wgmma_ss_112(float* d, uint32_t da, uint32_t db, int sd) {
  asm volatile("{\n.reg .pred p;\n.reg .b64 a, b;\nsetp.ne.b32 p, %58, 0;\nmov.b64 a, {%56, %59};\nmov.b64 b, {%57, %60};\n"
    "wgmma.mma_async.sync.aligned.m64n112k16.f32.bf16.bf16 {%0,%1,%2,%3,%4,%5,%6,%7,%8,%9,%10,%11,%12,%13,%14,%15,%16,%17,%18,%19,%20,%21,%22,%23,%24,%25,%26,%27,%28,%29,%30,%31,%32,%33,%34,%35,%36,%37,%38,%39,%40,%41,%42,%43,%44,%45,%46,%47,%48,%49,%50,%51,%52,%53,%54,%55}, a, b, p, 1, 1, 0, 1;\n}\n"
    : "+f"(d[0]),"+f"(d[1]),"+f"(d[2]),"+f"(d[3]),"+f"(d[4]),"+f"(d[5]),"+f"(d[6]),"+f"(d[7]),"+f"(d[8]),"+f"(d[9]),"+f"(d[10]),"+f"(d[11]),"+f"(d[12]),"+f"(d[13]),"+f"(d[14]),"+f"(d[15]),"+f"(d[16]),"+f"(d[17]),"+f"(d[18]),"+f"(d[19]),"+f"(d[20]),"+f"(d[21]),"+f"(d[22]),"+f"(d[23]),"+f"(d[24]),"+f"(d[25]),"+f"(d[26]),"+f"(d[27]),"+f"(d[28]),"+f"(d[29]),"+f"(d[30]),"+f"(d[31]),"+f"(d[32]),"+f"(d[33]),"+f"(d[34]),"+f"(d[35]),"+f"(d[36]),"+f"(d[37]),"+f"(d[38]),"+f"(d[39]),"+f"(d[40]),"+f"(d[41]),"+f"(d[42]),"+f"(d[43]),"+f"(d[44]),"+f"(d[45]),"+f"(d[46]),"+f"(d[47]),"+f"(d[48]),"+f"(d[49]),"+f"(d[50]),"+f"(d[51]),"+f"(d[52]),"+f"(d[53]),"+f"(d[54]),"+f"(d[55])
    : "r"(da), "r"(db), "r"(sd), "n"((uint32_t)(CA >> 32)), "n"((uint32_t)(CB >> 32)));
}
template<uint64_t CB> __device__ __forceinline__ void wgmma_rs_112(float* d, uint32_t a0, uint32_t a1, uint32_t a2, uint32_t a3, uint32_t db, int sd) {
  asm volatile("{\n.reg .pred p;\n.reg .b64 b;\nsetp.ne.b32 p, %61, 0;\nmov.b64 b, {%60, %62};\n"
    "wgmma.mma_async.sync.aligned.m64n112k16.f32.bf16.bf16 {%0,%1,%2,%3,%4,%5,%6,%7,%8,%9,%10,%11,%12,%13,%14,%15,%16,%17,%18,%19,%20,%21,%22,%23,%24,%25,%26,%27,%28,%29,%30,%31,%32,%33,%34,%35,%36,%37,%38,%39,%40,%41,%42,%43,%44,%45,%46,%47,%48,%49,%50,%51,%52,%53,%54,%55}, {%56,%57,%58,%59}, b, p, 1, 1, 1;\n}\n"
    : "+f"(d[0]),"+f"(d[1]),"+f"(d[2]),"+f"(d[3]),"+f"(d[4]),"+f"(d[5]),"+f"(d[6]),"+f"(d[7]),"+f"(d[8]),"+f"(d[9]),"+f"(d[10]),"+f"(d[11]),"+f"(d[12]),"+f"(d[13]),"+f"(d[14]),"+f"(d[15]),"+f"(d[16]),"+f"(d[17]),"+f"(d[18]),"+f"(d[19]),"+f"(d[20]),"+f"(d[21]),"+f"(d[22]),"+f"(d[23]),"+f"(d[24]),"+f"(d[25]),"+f"(d[26]),"+f"(d[27]),"+f"(d[28]),"+f"(d[29]),"+f"(d[30]),"+f"(d[31]),"+f"(d[32]),"+f"(d[33]),"+f"(d[34]),"+f"(d[35]),"+f"(d[36]),"+f"(d[37]),"+f"(d[38]),"+f"(d[39]),"+f"(d[40]),"+f"(d[41]),"+f"(d[42]),"+f"(d[43]),"+f"(d[44]),"+f"(d[45]),"+f"(d[46]),"+f"(d[47]),"+f"(d[48]),"+f"(d[49]),"+f"(d[50]),"+f"(d[51]),"+f"(d[52]),"+f"(d[53]),"+f"(d[54]),"+f"(d[55])
    : "r"(a0), "r"(a1), "r"(a2), "r"(a3), "r"(db), "r"(sd), "n"((uint32_t)(CB >> 32)));
}

constexpr int DM = 448;
constexpr int NCTA = 128;
#define MAPPING 1
#define GRID 132
#define PINGPONG 0
#define WIN 6
#define WIN_END 25
#define UNR_B 1
#define UNR_C 1
constexpr int kB = UNR_B, kC = UNR_C;
#define PACE 1
#define PACE_END 6
#define MAP_S 4
constexpr int SPIN_LIMIT = 1 << 22;

constexpr uint32_t OFF_X = 0, OFF_Y = 114688, OFF_MISC = 229376, SMEM_BYTES = 232448;
constexpr uint32_t Y_VR = 0, Y_K = 28672, Y_KOWN = 57344, Y_VOWN = 71680, Y_Q = 86016;
constexpr uint32_t HALF = 57344;
constexpr uint32_t M_BAR = OFF_MISC;
constexpr uint32_t M_ST = OFF_MISC + 512;
constexpr uint32_t M_G = OFF_MISC + 2304;
constexpr uint32_t M_EPOCH = OFF_MISC + 3040;
enum { B_XFULL = 0, B_FULLK = 7, B_FULLV = 8, B_FULLQ, B_KRFULL, B_VRFULL, B_WOFULL, B_XCH, B_FULL = 16, B_MOD1 = 28, B_MOD2, B_WMFULL,
       B_EMPTY = 32, B_XFREE = B_EMPTY + 12, B_GEMV, B_PEER,
       B_PUB = 47,
       B_WMFREE = 56, B_HRDY, B_GFULL = B_HRDY + 3, B_DONE = 31, B_DUMMY = B_GEMV };

__device__ uint32_t g_ticket;
__device__ __align__(128) uint32_t g_mod[8 * 6 * DM];
__device__ __align__(128) uint32_t g_flag[144 * 128];
constexpr int RB_WORDS = 262144, RB_KV = 0, RB_O = 57344, RB_X1 = 86016, RB_H2 = 143360, RB_ST = 258048;
__device__ __align__(128) uint32_t g_act[18 * RB_WORDS];
__device__ __align__(128) uint32_t g_wd[56 * 4 * 1792];
#define PROFH(id)
#define PROFH1(id)
#define PROFC(id)

struct alignas(64) Params {
    CUtensorMap wm, xm, qkv, wo, ga, ua, gb, ub, gc, uc, dn;
    const bf16 *x, *c, *wqkv, *wmod, *wg, *wu, *wd, *wop;
    bf16* out;
    uint32_t* actb;
    uint32_t zero;
};

__device__ __forceinline__ void mbar_init(uint32_t bar, int cnt) { asm volatile("mbarrier.init.shared::cta.b64 [%0], %1;" ::"r"(bar), "r"(cnt) : "memory"); }
__device__ __forceinline__ void mbar_expect_tx(uint32_t bar, uint32_t bytes) { asm volatile("mbarrier.arrive.expect_tx.shared::cta.b64 _, [%0], %1;" ::"r"(bar), "r"(bytes) : "memory"); }
__device__ __forceinline__ void mbar_arrive(uint32_t bar) { asm volatile("mbarrier.arrive.shared::cta.b64 _, [%0];" ::"r"(bar) : "memory"); }
__device__ __forceinline__ void mbar_wait(uint32_t bar, uint32_t parity) {
    uint32_t ok; int n = 0;
    do {
        asm volatile("{\n.reg .pred p;\nmbarrier.try_wait.parity.shared::cta.b64 p, [%1], %2;\nselp.u32 %0, 1, 0, p;\n}" : "=r"(ok) : "r"(bar), "r"(parity) : "memory");
        if (++n > SPIN_LIMIT) __trap();
    } while (!ok);
}
__device__ __forceinline__ void mbar_wait_c(uint32_t bar, uint32_t parity) {
    asm volatile("{\n.reg .pred p;\nWL:\nmbarrier.try_wait.parity.shared::cta.b64 p, [%0], %1;\n@!p bra WL;\n}" ::"r"(bar), "r"(parity) : "memory");
}
__device__ __forceinline__ void mbar_wait_cluster(uint32_t bar, uint32_t parity) {
    uint32_t ok; int n = 0;
    do {
        asm volatile("{\n.reg .pred p;\nmbarrier.try_wait.parity.acquire.cluster.shared::cta.b64 p, [%1], %2;\nselp.u32 %0, 1, 0, p;\n}" : "=r"(ok) : "r"(bar), "r"(parity) : "memory");
        if (++n > SPIN_LIMIT) __trap();
    } while (!ok);
}
__device__ __forceinline__ void warp_arrive(uint32_t bar) {
    __syncwarp();
    asm volatile("{\n.reg .pred p;\nelect.sync _|p, 0xffffffff;\n@p mbarrier.arrive.shared::cta.b64 _, [%0];\n}" ::"r"(bar) : "memory");
}
__device__ __forceinline__ int opaque(int v) { return __shfl_sync(~0u, v, 0); }
__device__ __forceinline__ int fresh_tid() { int v; asm volatile("mov.u32 %0, %%tid.x;" : "=r"(v)); return v; }
__device__ __forceinline__ void bar_sync(int id, int n) { asm volatile("bar.sync %0, %1;" ::"r"(id), "r"(n) : "memory"); }
__device__ __forceinline__ void bar_arrive(int id, int n) { asm volatile("bar.arrive %0, %1;" ::"r"(id), "r"(n) : "memory"); }
__device__ __forceinline__ void fence_async_smem() { asm volatile("fence.proxy.async.shared::cta;" ::: "memory"); }
__device__ __forceinline__ void fence_async_global() { asm volatile("fence.proxy.async.global;" ::: "memory"); }
__device__ __forceinline__ void fence_gpu() { asm volatile("fence.release.gpu;" ::: "memory"); }
__device__ __forceinline__ void tma3(uint32_t dst, const CUtensorMap* m, int c0, int c1, int c2, uint32_t bar) {
    asm volatile("cp.async.bulk.tensor.3d.shared::cluster.global.mbarrier::complete_tx::bytes [%0], [%1, {%3, %4, %5}], [%2];"
                 ::"r"(dst), "l"(m), "r"(bar), "r"(c0), "r"(c1), "r"(c2) : "memory");
}
__device__ __forceinline__ void bulk_load(uint32_t dst, const void* src, uint32_t bytes, uint32_t bar) {
    asm volatile("cp.async.bulk.shared::cluster.global.mbarrier::complete_tx::bytes [%0], [%1], %2, [%3];" ::"r"(dst), "l"(src), "r"(bytes), "r"(bar) : "memory");
}
__device__ __forceinline__ void expect_e(uint32_t bar, uint32_t bytes) {
    asm volatile("{\n.reg .pred p;\nelect.sync _|p, 0xffffffff;\n@p mbarrier.arrive.expect_tx.shared::cta.b64 _, [%0], %1;\n}" ::"r"(bar), "r"(bytes) : "memory");
}
__device__ __forceinline__ void tma3_e(uint32_t dst, const CUtensorMap* m, int c0, int c1, int c2, uint32_t bar) {
    asm volatile("{\n.reg .pred p;\nelect.sync _|p, 0xffffffff;\n@p cp.async.bulk.tensor.3d.shared::cluster.global.mbarrier::complete_tx::bytes [%0], [%1, {%3, %4, %5}], [%2];\n}"
                 ::"r"(dst), "l"(m), "r"(bar), "r"(c0), "r"(c1), "r"(c2) : "memory");
}
__device__ __forceinline__ void bulk_e(uint32_t dst, const void* src, uint32_t bytes, uint32_t bar) {
    asm volatile("{\n.reg .pred p;\nelect.sync _|p, 0xffffffff;\n@p cp.async.bulk.shared::cluster.global.mbarrier::complete_tx::bytes [%0], [%1], %2, [%3];\n}"
                 ::"r"(dst), "l"(src), "r"(bytes), "r"(bar) : "memory");
}
__device__ __forceinline__ void init_e(uint32_t bar, int cnt) {
    asm volatile("{\n.reg .pred p;\nelect.sync _|p, 0xffffffff;\n@p mbarrier.init.shared::cta.b64 [%0], %1;\n}" ::"r"(bar), "r"(cnt) : "memory");
}
__device__ __forceinline__ void l2_prefetch_e(const void* src, uint32_t bytes) {
    asm volatile("{\n.reg .pred p;\nelect.sync _|p, 0xffffffff;\n@p cp.async.bulk.prefetch.L2.global [%0], %1;\n}" ::"l"(src), "r"(bytes) : "memory");
}
__device__ __forceinline__ uint32_t ld_relaxed(const uint32_t* p) { uint32_t v; asm volatile("ld.relaxed.gpu.global.u32 %0, [%1];" : "=r"(v) : "l"(p) : "memory"); return v; }
__device__ __forceinline__ void st_relaxed(uint32_t* p, uint32_t v) { asm volatile("st.relaxed.gpu.global.u32 [%0], %1;" ::"l"(p), "r"(v) : "memory"); }
__device__ __forceinline__ uint4 ld_relaxed4(const uint4* p) { uint4 v; asm volatile("ld.relaxed.gpu.global.v4.u32 {%0,%1,%2,%3}, [%4];" : "=r"(v.x), "=r"(v.y), "=r"(v.z), "=r"(v.w) : "l"(p) : "memory"); return v; }
__device__ __forceinline__ void st_relaxed4(uint4* p, uint4 v) { asm volatile("st.relaxed.gpu.global.v4.u32 [%0], {%1,%2,%3,%4};" ::"l"(p), "r"(v.x), "r"(v.y), "r"(v.z), "r"(v.w) : "memory"); }
__device__ __forceinline__ uint4 ldg_nc4(const void* p) { uint4 v; asm volatile("ld.global.nc.L1::no_allocate.v4.u32 {%0,%1,%2,%3}, [%4];" : "=r"(v.x), "=r"(v.y), "=r"(v.z), "=r"(v.w) : "l"(p)); return v; }
__device__ __forceinline__ uint32_t ldg_nc(const void* p) { uint32_t v; asm volatile("ld.global.nc.u32 %0, [%1];" : "=r"(v) : "l"(p)); return v; }
__device__ __forceinline__ uint32_t ld_acquire(const uint32_t* p) { uint32_t v; asm volatile("ld.acquire.gpu.global.u32 %0, [%1];" : "=r"(v) : "l"(p) : "memory"); return v; }
__device__ __forceinline__ uint4 lds4(uint32_t a) { uint4 v; asm volatile("ld.shared.v4.u32 {%0,%1,%2,%3}, [%4];" : "=r"(v.x), "=r"(v.y), "=r"(v.z), "=r"(v.w) : "r"(a) : "memory"); return v; }
__device__ __forceinline__ float2 lds2f(uint32_t a) { float2 v; asm volatile("ld.shared.v2.f32 {%0,%1}, [%2];" : "=f"(v.x), "=f"(v.y) : "r"(a) : "memory"); return v; }
__device__ __forceinline__ uint32_t lds1(uint32_t a) { uint32_t v; asm volatile("ld.shared.u32 %0, [%1];" : "=r"(v) : "r"(a) : "memory"); return v; }
__device__ __forceinline__ void sts4(uint32_t a, uint4 v) { asm volatile("st.shared.v4.u32 [%0], {%1,%2,%3,%4};" ::"r"(a), "r"(v.x), "r"(v.y), "r"(v.z), "r"(v.w) : "memory"); }
__device__ __forceinline__ void sts2(uint32_t a, uint32_t x, uint32_t y) { asm volatile("st.shared.v2.u32 [%0], {%1,%2};" ::"r"(a), "r"(x), "r"(y) : "memory"); }
__device__ __forceinline__ void sts1(uint32_t a, uint32_t v) { asm volatile("st.shared.u32 [%0], %1;" ::"r"(a), "r"(v) : "memory"); }
__device__ __forceinline__ void stsm4(uint32_t a, uint32_t r0, uint32_t r1, uint32_t r2, uint32_t r3) {
    asm volatile("stmatrix.sync.aligned.m8n8.x4.shared.b16 [%0], {%1,%2,%3,%4};" ::"r"(a), "r"(r0), "r"(r1), "r"(r2), "r"(r3));
}
__device__ __forceinline__ uint32_t pack2(float lo, float hi) { uint32_t r; asm("cvt.rn.bf16x2.f32 %0, %1, %2;" : "=r"(r) : "f"(hi), "f"(lo)); return r; }
__device__ __forceinline__ uint32_t pack2_relu(float lo, float hi) { uint32_t r; asm("cvt.rn.relu.bf16x2.f32 %0, %1, %2;" : "=r"(r) : "f"(hi), "f"(lo)); return r; }
__device__ __forceinline__ uint32_t hfma2(uint32_t a, uint32_t b, uint32_t c) { uint32_t r; asm("fma.rn.bf16x2 %0, %1, %2, %3;" : "=r"(r) : "r"(a), "r"(b), "r"(c)); return r; }
__device__ __forceinline__ uint32_t hmul2(uint32_t a, uint32_t b) { uint32_t r; asm("mul.rn.bf16x2 %0, %1, %2;" : "=r"(r) : "r"(a), "r"(b)); return r; }
__device__ __forceinline__ float bf_lo(uint32_t v) { return __uint_as_float(v << 16); }
__device__ __forceinline__ float bf_hi(uint32_t v) { return __uint_as_float(v & 0xFFFF0000u); }
__device__ __forceinline__ float bf_round(float v) { return bf_lo(pack2(v, 0.f)); }
__device__ __forceinline__ float ex2(float x) { float r; asm("ex2.approx.ftz.f32 %0, %1;" : "=f"(r) : "f"(x)); return r; }
__device__ __forceinline__ void mma16816(float* d, uint32_t a0, uint32_t a1, uint32_t a2, uint32_t a3, uint32_t b0, uint32_t b1) {
    asm("mma.sync.aligned.m16n8k16.row.col.f32.bf16.bf16.f32 {%0,%1,%2,%3}, {%4,%5,%6,%7}, {%8,%9}, {%0,%1,%2,%3};"
        : "+f"(d[0]), "+f"(d[1]), "+f"(d[2]), "+f"(d[3]) : "r"(a0), "r"(a1), "r"(a2), "r"(a3), "r"(b0), "r"(b1));
}
__device__ __forceinline__ void mma16816_first(float* d, uint32_t a0, uint32_t a1, uint32_t a2, uint32_t a3, uint32_t b0, uint32_t b1) {
    asm volatile("mma.sync.aligned.m16n8k16.row.col.f32.bf16.bf16.f32 {%0,%1,%2,%3}, {%4,%5,%6,%7}, {%8,%9}, {%10,%10,%10,%10};"
        : "=f"(d[0]), "=f"(d[1]), "=f"(d[2]), "=f"(d[3]) : "r"(a0), "r"(a1), "r"(a2), "r"(a3), "r"(b0), "r"(b1), "f"(0.f));
}
__device__ __forceinline__ void mma16816_v(float* d, uint32_t a0, uint32_t a1, uint32_t a2, uint32_t a3, uint32_t b0, uint32_t b1) {
    asm volatile("mma.sync.aligned.m16n8k16.row.col.f32.bf16.bf16.f32 {%0,%1,%2,%3}, {%4,%5,%6,%7}, {%8,%9}, {%0,%1,%2,%3};"
        : "+f"(d[0]), "+f"(d[1]), "+f"(d[2]), "+f"(d[3]) : "r"(a0), "r"(a1), "r"(a2), "r"(a3), "r"(b0), "r"(b1));
}
__device__ __forceinline__ void mma1688(float* d, uint32_t a0, uint32_t a1, uint32_t b0) {
    asm("mma.sync.aligned.m16n8k8.row.col.f32.bf16.bf16.f32 {%0,%1,%2,%3}, {%4,%5}, {%6}, {%0,%1,%2,%3};"
        : "+f"(d[0]), "+f"(d[1]), "+f"(d[2]), "+f"(d[3]) : "r"(a0), "r"(a1), "r"(b0));
}
__device__ __forceinline__ void ldsm4(uint32_t a, uint32_t* r) {
    asm volatile("ldmatrix.sync.aligned.m8n8.x4.shared.b16 {%0,%1,%2,%3}, [%4];" : "=r"(r[0]), "=r"(r[1]), "=r"(r[2]), "=r"(r[3]) : "r"(a));
}
__device__ __forceinline__ void ldsm4t(uint32_t a, uint32_t* r) {
    asm volatile("ldmatrix.sync.aligned.m8n8.x4.trans.shared.b16 {%0,%1,%2,%3}, [%4];" : "=r"(r[0]), "=r"(r[1]), "=r"(r[2]), "=r"(r[3]) : "r"(a));
}
__device__ __forceinline__ float rcp(float x) { float r; asm("rcp.approx.ftz.f32 %0, %1;" : "=f"(r) : "f"(x)); return r; }
__device__ __forceinline__ uint2 ld_relaxed2(const void* p) { uint2 v; asm volatile("ld.relaxed.gpu.global.v2.u32 {%0,%1}, [%2];" : "=r"(v.x), "=r"(v.y) : "l"(p) : "memory"); return v; }
__device__ __forceinline__ void st_relaxed2(void* p, uint32_t x, uint32_t y) { asm volatile("st.relaxed.gpu.global.v2.u32 [%0], {%1,%2};" ::"l"(p), "r"(max(x, 1u)), "r"(max(y, 1u)) : "memory"); }
__host__ __device__ constexpr uint64_t dconst(uint32_t lbo, uint32_t sbo, uint32_t swz) {
    return ((uint64_t)(lbo >> 4) << 16) | ((uint64_t)(sbo >> 4) << 32) | ((uint64_t)swz << 62);
}
__device__ __forceinline__ uint32_t mkdesc(uint32_t addr, uint64_t c) { return (uint32_t)c | ((addr & 0x3FFFF) >> 4); }
#define WG_FENCE() asm volatile("wgmma.fence.sync.aligned;" ::: "memory")
#define WG_COMMIT() asm volatile("wgmma.commit_group.sync.aligned;" ::: "memory")
#define WG_WAIT(n) asm volatile("wgmma.wait_group.sync.aligned %0;" ::"n"(n) : "memory")
template <int N> __device__ __forceinline__ void reg_fence(float* d) {
#pragma unroll
    for (int i = 0; i < N; i++) asm volatile("" : "+f"(d[i])::"memory");
}
template <int N> __device__ __forceinline__ void reg_def(float* d) {
#pragma unroll
    for (int i = 0; i < N; i++) asm volatile("" : "=f"(d[i]));
}
template <int N> __device__ __forceinline__ void reg_def(uint32_t* d) {
#pragma unroll
    for (int i = 0; i < N; i++) asm volatile("" : "=r"(d[i]));
}
__device__ __forceinline__ bool is_unset(uint4 v) { return min(min(v.x, v.y), min(v.z, v.w)) == 0u; }
__device__ __forceinline__ uint4 nz4(uint32_t a, uint32_t b, uint32_t c, uint32_t d) { return make_uint4(max(a, 1u), max(b, 1u), max(c, 1u), max(d, 1u)); }
__device__ __forceinline__ void wait_flags(const uint32_t* p, uint32_t target, uint32_t mask) {
    int n = 0;
    while (~__ballot_sync(~0u, (int)(ld_relaxed(p) - target) >= 0) & mask) { if (++n > SPIN_LIMIT) __trap(); }
    asm volatile("fence.acquire.gpu;" ::: "memory");
}
__device__ __forceinline__ float silu_bf(uint32_t cbits) {
    const float c = __uint_as_float(cbits << 16);
    return bf_round(__fdividef(c, 1.f + fminf(ex2(-1.4426950408889634f * c), 1e30f)));
}
__device__ __forceinline__ void gemv_part(uint32_t wmbuf, int npanel, int wp, int lane) {
    const uint32_t wa = wmbuf + wp * 512 + (8 * (lane >> 4) + (lane & 7)) * 32 + ((lane >> 3) & 1) * 16;
    uint2 B[4];
#pragma unroll
    for (int i = 0; i < 4; i++) { const float2 v = lds2f(wmbuf + 28672 + (wp + 8 * i) * 32 + (lane & 3) * 8); B[i] = make_uint2(__float_as_uint(v.x), __float_as_uint(v.y)); }
#pragma unroll 1
    for (int pn = 0; pn < npanel; pn++) {
        float d[4] = {};
        uint32_t A[16];
#pragma unroll
        for (int i = 0; i < 4; i++) ldsm4t(wa + pn * 14336 + (i < 3 || wp < 4 ? i : 0) * 4096, A + 4 * i);
#pragma unroll
        for (int i = 0; i < 4; i++) mma16816(d, A[4 * i], A[4 * i + 1], A[4 * i + 2], A[4 * i + 3], B[i].x, B[i].y);
        if ((lane & 3) == 0) {
            sts1(wmbuf + 29696 + (wp * 32 + pn * 16 + (lane >> 2)) * 4, __float_as_uint(d[0]));
            sts1(wmbuf + 29696 + (wp * 32 + pn * 16 + 8 + (lane >> 2)) * 4, __float_as_uint(d[2]));
        }
    }
}
__device__ __forceinline__ int pass_f(int fs, int ps) { return 224 * fs + ((fs & 1) ? (ps == 0 ? 96 : ps == 1 ? 32 : 0) : (ps == 0 ? 0 : ps == 1 ? 128 : 192)); }
__device__ __forceinline__ constexpr uint32_t slot_off(int l) { return l * 16384; }
__device__ __forceinline__ void x1_fix(uint32_t* x, const uint32_t* g) {
    do {
#pragma unroll
        for (int i = 0; i < 8; i++) x[i] = ld_relaxed(g + (i >> 1) * 256 + (i & 1) * 32);
    } while (__any_sync(~0u, min(min(min(x[0], x[1]), min(x[2], x[3])), min(min(x[4], x[5]), min(x[6], x[7]))) == 0u));
}
__device__ __forceinline__ void ln_coeffs(float mean, float msq, uint32_t& r2, uint32_t& n2) {
    const float rs = bf_round(rsqrtf(fmaxf(msq - mean * mean, 0.f) + 1e-5f));
    r2 = pack2(rs, rs);
    n2 = pack2(-mean * rs, -mean * rs);
}

#define LOADW bulk_e(dst, g_wd + (size_t)((f >> 5) * 4 + nq) * 1792, 7168, bar);
template <int sec> __device__ __forceinline__ void ring_loader(const Params& p, uint32_t sb_, int r_, int j_, int lane) {
    const uint32_t sb = opaque(sb_);
    const int r = opaque(r_), j = opaque(j_), nq = j >> 1, fs = 4 * (j & 1) + nq;
    const int fa = pass_f(fs, 0), fb = pass_f(fs, 1), fc = pass_f(fs, 2);
#define BAR(i) (sb + M_BAR + 8 * (i))
#define kh (j & 1)
            int sl = 0;
            mbar_wait(BAR(B_PUB + 2), 0);
            wait_flags(g_flag + (8 * r + j) * 128 + 96 + lane, lds1(sb + M_EPOCH) + 1, 0xFFFFu);
            fence_async_global();
#pragma unroll 1
            for (int s = 0; s < 28; s++) {
                if (s >= PACE && s < PACE_END) mbar_wait(BAR(B_FULL + s - PACE), 0);
                const int ps = s < 14 ? 0 : s < 21 ? 1 : 2;
                const uint32_t half = ps < 2 ? 8192 : 4096;
                mbar_wait(BAR(B_EMPTY + sl), (s >= 7 && s < 14) || s >= 21);
                expect_e(BAR(B_FULL + sl), half);
                tma3_e(sb + slot_off(sl) + sec * half, &p.ga + 2 * ps + sec, 0, ps ? 64 * sl : 32 * s, ps == 0 ? fa >> 6 : ps == 1 ? fb >> 6 : fc >> 5, BAR(B_FULL + sl));
                sl = sl == 6 ? 0 : sl + 1;
            }
            if (!sec) PROFH(3);
#pragma unroll 1
            for (int e = 0; e < 4; e++) {
                const uint32_t dst = sb + slot_off(e) + sec * 8192, bar = BAR(B_FULL + e);
                const int f = (e < 2 ? fa + 64 * e : e == 2 ? fb : fc) + 32 * sec;
                mbar_wait(BAR(B_EMPTY + e), 0);
                expect_e(bar, e == 3 && sec ? 0 : 7168);
                if (!(e == 3 && sec)) { LOADW }
            }
            sl = 4;
            int e = 4;
#pragma unroll 1
            for (int grp = 0; grp < 9; grp++) {
                const int ps = grp >= 6 ? 2 : grp >= 3 ? 1 : 0;
                int sidx = grp - 3 * ps;
                if (sec && sidx == 0) { mbar_wait(BAR(B_HRDY + ps), 0); fence_async_global(); }
                sidx += sidx >= nq;
                int f = pass_f(4 * kh + sidx, ps);
#pragma unroll 1
                for (int k = 4 >> ps; k > 0; k--, e++, f += 32) {
                    const uint32_t dst = sb + slot_off(sl), bar = BAR(B_FULL + sl);
                    mbar_wait(BAR(B_EMPTY + sl), e >= 12 && e < 24);
                    if (e < WIN_END && e >= WIN) mbar_wait(BAR(B_FULL + (sl >= WIN ? sl - WIN : sl + 12 - WIN)), e - WIN >= 12);
                    expect_e(bar, sec ? 8192 : 7168);
                    if (!sec) { LOADW }
                    else bulk_e(dst + 8192, p.actb + (size_t)r * RB_WORDS + RB_H2 + f * 64, 8192, bar);
                    sl = sl == 11 ? 0 : sl + 1;
                }
            }
            if (!sec) PROFH(4);
}

__global__ void __cluster_dims__(2, 1, 1) __launch_bounds__(384, 1) fused_block_kernel(const __grid_constant__ Params p) {
    extern __shared__ __align__(1024) unsigned char smem[];
    const uint32_t sb = (uint32_t)__cvta_generic_to_shared(smem);
    const int tid = threadIdx.x, lane = tid & 31, warp = __shfl_sync(~0u, tid >> 5, 0);
    const int m = blockIdx.x >> 1;
    int r, nq;
    {
        int g, i;
        if (m < MAP_S) { g = m < 4 ? 15 : 16; i = m & 3; }
        else if (m < MAP_S + 32) { g = (m - MAP_S) & 7; i = (m - MAP_S) >> 3; }
        else if (m < MAP_S + 60) { i = (m - MAP_S - 32) / 7; g = 8 + (m - MAP_S - 32) - 7 * i; }
        else { g = 16; i = m & 3; }
        r = g; nq = i;
    }
    const int j = opaque(2 * nq + (blockIdx.x & 1)), b = 8 * r + j, fs = 4 * kh + nq;
#define act (p.actb + (size_t)r * RB_WORDS)
    const uint32_t sc = r == 16;
    if (lane == 0 && warp < 9 && warp != 6 && warp != 7) {
        const int i0 = warp == 8 ? 0 : 8 + 8 * warp, cnt = warp == 0 || warp == 8 ? 1 : warp < 3 ? 2 : 8;
#pragma unroll
        for (int k = 0; k < 8; k++) if (i0 + k != B_WMFULL) mbar_init(BAR(i0 + k), cnt);
        asm volatile("fence.mbarrier_init.release.cluster;" ::: "memory");
        fence_async_smem();
    }

    if (warp < 8) {
        const int w = warp >> 2, wi = warp & 3;
#define COORDS const int t = fresh_tid() & 127, lane = t & 31, q = lane & 3, lr = lane >> 2, ra = 64 * w + 16 * wi + lr; \
        const uint32_t lx = (lane >> 4) ^ (lane & 7), mrow = (64 * w + 16 * wi + ((lane >> 3) & 1) * 8 + (lane & 7)) * 128; \
        (void)q; (void)lr; (void)ra; (void)lx; (void)mrow;
        const int sid = 2 * (j & 3) + w;
#define RUN(k) (!sc || sid == (k))
#define WAIT(i, par) mbar_wait_c(BAR(i), (par) | sc)
        constexpr uint64_t DB128 = dconst(4096, 1024, 1);
        bar_arrive(9, 384);
        bar_sync(0, 384);
        asm volatile("barrier.cluster.arrive.relaxed.aligned;" ::: "memory");
        asm volatile("setmaxnreg.inc.sync.aligned.u32 224;");
        PROFC(0);
        uint32_t xr[16];
        {
            COORDS
            uint32_t h[112];
            if (RUN(0)) {
                float ds[4] = {}, da[2][4] = {}, db[2][4] = {};
                const uint32_t ONE2 = 0x3F803F80u;
                if (kh == 0) { WAIT(B_WMFULL, 0); gemv_part(sb + OFF_Y + HALF, 1, warp, lane); warp_arrive(BAR(B_GEMV)); }
#pragma unroll
                for (int kb = 0; kb < 7; kb++) {
                    WAIT(B_XFULL + kb, 0);
#pragma unroll
                    for (int k4 = 0; k4 < 4; k4++) ldsm4(sb + OFF_X + mrow + kb * 16384 + (((2 * k4) ^ lx) << 4), h + 16 * kb + 4 * k4);
#pragma unroll
                    for (int k4 = 0; k4 < 4; k4++) {
                        const uint32_t* f = h + 16 * kb + 4 * k4;
                        mma16816(ds, f[0], f[1], f[2], f[3], ONE2, ONE2);
                        mma1688(da[0], f[0], f[1], f[0]); mma1688(db[0], f[0], f[1], f[1]);
                        mma1688(da[1], f[2], f[3], f[2]); mma1688(db[1], f[2], f[3], f[3]);
                    }
                }
#pragma unroll
                for (int i = 0; i < 4; i++) {
                    const int ch = 7 * j + 2 * i + (lane >> 4);
                    ldsm4(sb + OFF_X + mrow + (ch >> 3) * 16384 + (((ch ^ lane) & 7) << 4), xr + 4 * i);
                }
                warp_arrive(BAR(B_XFREE));
                float qa = (lr & 1) ? da[0][1] + da[1][1] : da[0][0] + da[1][0];
                float qb = (lr & 1) ? db[0][3] + db[1][3] : db[0][2] + db[1][2];
                const int src = (lane & ~3) | (lr >> 1);
                qa = __shfl_sync(~0u, qa, src);
                qb = __shfl_sync(~0u, qb, src);
                uint32_t ra2, na2, rb2, nb2;
                ln_coeffs(ds[0] * (1.f / DM), qa * (1.f / DM), ra2, na2);
                ln_coeffs(ds[2] * (1.f / DM), qb * (1.f / DM), rb2, nb2);
#pragma unroll
                for (int i = 0; i < 112; i += 2) { h[i] = hfma2(h[i], ra2, na2); h[i + 1] = hfma2(h[i + 1], rb2, nb2); }
                if (kh == 1) { WAIT(B_WMFULL, 0); gemv_part(sb + OFF_Y + HALF, 2, warp, lane); warp_arrive(BAR(B_GEMV)); }
            } else { reg_def<112>(h); reg_def<16>(xr); }
            PROFC(1);
            if (RUN(1)) {
                float ak[28], av[28], aq[28];
                uint32_t kp[14], vp[14];
                const uint32_t bk0 = mkdesc(sb + OFF_Y, DB128) + kh, bv0 = mkdesc(sb + OFF_Y + HALF, DB128) + kh, bq0 = mkdesc(sb + OFF_X, DB128) + kh;
                uint32_t* kvg = act + RB_KV + j * 7168 + (8 * w + 2 * wi) * 224 + lane;
                WAIT(B_FULLK, 0);
                WAIT(B_MOD1, 0);
                PROFC(2);
                reg_def<28>(ak);
#pragma unroll
                for (int g4 = 0; g4 < 4; g4++) {
#pragma unroll
                    for (int ks = 7 * g4; ks < 7 * g4 + 7; ks++) {
                        const uint4 st = *(const uint4*)(smem + M_ST + ks * 64 + q * 16);
                        h[4 * ks] = hfma2(h[4 * ks], st.x, st.y); h[4 * ks + 1] = hfma2(h[4 * ks + 1], st.x, st.y);
                        h[4 * ks + 2] = hfma2(h[4 * ks + 2], st.z, st.w); h[4 * ks + 3] = hfma2(h[4 * ks + 3], st.z, st.w);
                    }
                    WG_FENCE();
#pragma unroll
                    for (int ks = 7 * g4; ks < 7 * g4 + 7; ks++) wgmma_rs_56<DB128>(ak, h[4 * ks], h[4 * ks + 1], h[4 * ks + 2], h[4 * ks + 3], bk0 + ks * 128, ks != 0);
                }
                WG_COMMIT();
                PROFC(3);
                WAIT(B_FULLV, 0);
                reg_def<28>(av);
                WG_FENCE();
#pragma unroll
                for (int ks = 0; ks < 8; ks++) wgmma_rs_56<DB128>(av, h[4 * ks], h[4 * ks + 1], h[4 * ks + 2], h[4 * ks + 3], bv0 + ks * 128, ks != 0);
                WG_COMMIT();
                WG_WAIT(1);
                reg_fence<28>(ak);
#pragma unroll
                for (int g = 0; g < 7; g++) {
                    kp[2 * g] = pack2(ak[4 * g], ak[4 * g + 1]); kp[2 * g + 1] = pack2(ak[4 * g + 2], ak[4 * g + 3]);
                    kvg[g * 32] = kp[2 * g]; kvg[224 + g * 32] = kp[2 * g + 1];
                }
                warp_arrive(BAR(B_PUB));
                PROFC(4);
                WG_FENCE();
#pragma unroll
                for (int ks = 8; ks < 28; ks++) wgmma_rs_56<DB128>(av, h[4 * ks], h[4 * ks + 1], h[4 * ks + 2], h[4 * ks + 3], bv0 + ks * 128, 1);
                WG_COMMIT();
                WAIT(B_FULLQ, 0);
                reg_def<28>(aq);
                WG_FENCE();
#pragma unroll
                for (int ks = 0; ks < 8; ks++) wgmma_rs_56<DB128>(aq, h[4 * ks], h[4 * ks + 1], h[4 * ks + 2], h[4 * ks + 3], bq0 + ks * 128, ks != 0);
                WG_COMMIT();
                WG_WAIT(1);
                reg_fence<28>(av);
#pragma unroll
                for (int g = 0; g < 7; g++) {
                    vp[2 * g] = pack2(av[4 * g], av[4 * g + 1]); vp[2 * g + 1] = pack2(av[4 * g + 2], av[4 * g + 3]);
                    kvg[3584 + g * 32] = vp[2 * g]; kvg[3584 + 224 + g * 32] = vp[2 * g + 1];
                }
                warp_arrive(BAR(B_PUB + 1));
                PROFC(5);
                WG_FENCE();
#pragma unroll
                for (int ks = 8; ks < 28; ks++) wgmma_rs_56<DB128>(aq, h[4 * ks], h[4 * ks + 1], h[4 * ks + 2], h[4 * ks + 3], bq0 + ks * 128, 1);
                WG_COMMIT();
                WAIT(B_PUB + 1, 0);
                const uint32_t ko = sb + OFF_Y + Y_KOWN + (8 * w + 2 * wi) * 896 + lane * 4;
                const uint32_t qo = sb + OFF_Y + Y_Q + (8 * w + 2 * wi) * 1024 + lane * 4;
#pragma unroll
                for (int g = 0; g < 7; g++) {
                    sts1(ko + g * 128, kp[2 * g]); sts1(ko + 896 + g * 128, kp[2 * g + 1]);
                    sts1(ko + (Y_VOWN - Y_KOWN) + g * 128, vp[2 * g]); sts1(ko + (Y_VOWN - Y_KOWN) + 896 + g * 128, vp[2 * g + 1]);
                }
                WG_WAIT(0);
                reg_fence<28>(aq);
                __syncwarp();
                if (lane < 3 && w == 1) mbar_arrive(BAR(B_EMPTY + lane));
#pragma unroll
                for (int g = 0; g < 7; g++) {
                    const uint32_t q0 = pack2(aq[4 * g], aq[4 * g + 1]), q1 = pack2(aq[4 * g + 2], aq[4 * g + 3]);
                    if (g == 3) {
                        sts1(qo + 3 * 128, q < 2 ? q0 : 0u); sts1(qo + 1024 + 3 * 128, q < 2 ? q1 : 0u);
                        sts1(qo + 4 * 128, q < 2 ? 0u : q0); sts1(qo + 1024 + 4 * 128, q < 2 ? 0u : q1);
                    } else {
                        const int ch = g < 3 ? g : g + 1;
                        sts1(qo + ch * 128, q0); sts1(qo + 1024 + ch * 128, q1);
                    }
                }
                if (!sc) bar_sync(3, 256);
            }
        }
        PROFC(6);
        WAIT(B_KRFULL, 0);
        PROFC(7);
        if (RUN(2)) {
#pragma unroll 1
            for (int hf = sc; hf < 2; hf++) {
                COORDS
                float s[136];
                float na = 0.f, nb = 0.f;
                const float CS = 0.18898223650461361f * 1.4426950408889634f;
                const int kg0 = 8 * hf + 2 * wi;
                const int pmin = 16 - 8 * r - 4 * hf - wi;
                const float NEG = __int_as_float(0xFF800000);
                {
                    uint32_t F[8];
                    const uint32_t qa = sb + OFF_Y + Y_Q + (kg0 + ((lane >> 3) & 1)) * 1024 + (4 * w + (lane >> 4)) * 128 + (lane & 7) * 16;
                    ldsm4(qa, F); ldsm4(qa + 256, F + 4);
                    uint32_t ka = sb + OFF_Y + Y_K + kg0 * 896 + (3 * w + (lane >> 3)) * 128 + (lane & 7) * 16;
#pragma unroll
                    for (int g = 0; g < 34; g++) {
                        uint32_t B[4];
                        if (g >= 12 && g % 4 == 0) ka += __float_as_uint(s[4 * (g - 12)]) & p.zero;
                        ldsm4(ka + g * 896, B);
                        mma16816_first(s + 4 * g, F[0], F[1], F[2], F[3], B[0], B[1]);
                        mma16816_v(s + 4 * g, F[4], F[5], F[6], F[7], B[2], B[3]);
                    }
                    const bool c0 = 2 * q > lr, c1 = 2 * q + 1 > lr;
                    if (!c0) { s[0] = NEG; s[6] = NEG; }
                    if (!c1) { s[1] = NEG; s[7] = NEG; }
                    s[2] = NEG; s[3] = NEG;
                    if (c0) { s[128] = NEG; s[134] = NEG; }
                    if (c1) { s[129] = NEG; s[135] = NEG; }
                    s[132] = NEG; s[133] = NEG;
                    float ma = NEG, mb = NEG;
#pragma unroll
                    for (int pp = 0; pp < 17; pp++) {
                        const float* e = s + 8 * pp;
                        const float bias = pp < pmin ? NEG : 0.f;
                        ma = fmaxf(ma, fmaxf(fmaxf(e[0], e[1]), fmaxf(e[4], e[5])) + bias);
                        mb = fmaxf(mb, fmaxf(fmaxf(e[2], e[3]), fmaxf(e[6], e[7])) + bias);
                    }
                    ma = fmaxf(ma, __shfl_xor_sync(~0u, ma, 1)); mb = fmaxf(mb, __shfl_xor_sync(~0u, mb, 1));
                    ma = fmaxf(ma, __shfl_xor_sync(~0u, ma, 2)); mb = fmaxf(mb, __shfl_xor_sync(~0u, mb, 2));
                    na = -ma * CS; nb = -mb * CS;
                }
                PROFC(8 + 3 * hf);
                {
                    WAIT(B_VRFULL, 0);
                    float o[16] = {}, rs[4] = {};
                    uint32_t pk[2];
                    const uint32_t va = sb + OFF_Y + Y_VR + (kg0 + ((lane >> 3) & 1)) * 896 + (3 * w + (lane >> 4)) * 128 + (lane & 7) * 16;
#pragma unroll
                    for (int pp = 0; pp < 17; pp++) {
                        uint32_t B[8];
                        const uint32_t v = va + pp * 1792 + (pp == 16 || (pp >= 9 && kg0 + 2 * pp >= 32) ? Y_VOWN - 32 * 896 : 0);
                        ldsm4t(v, B); ldsm4t(v + 256, B + 4);
                        float e[8];
                        const float bias = __uint_as_float((pp < pmin ? 0xFF800000u : 0u) | ((pp < 2 ? B[0] : pk[pp & 1]) & p.zero));
#pragma unroll
                        for (int i = 0; i < 8; i++) e[i] = ex2(fmaf(s[8 * pp + i], CS, ((i & 2) ? nb : na) + bias));
                        const uint32_t p0 = pack2(e[0], e[1]), p1 = pack2(e[2], e[3]), p2 = pack2(e[4], e[5]), p3 = pack2(e[6], e[7]);
                        pk[pp & 1] = p3;
                        mma16816(rs, p0, p1, p2, p3, 0x3F803F80u, 0x3F803F80u);
#pragma unroll
                        for (int g = 0; g < 4; g++) mma16816(o + 4 * g, p0, p1, p2, p3, B[2 * g], B[2 * g + 1]);
                    }
                    PROFC(9 + 3 * hf);
                    const float ia = rcp(rs[0]), ib = rcp(rs[2]);
                    uint32_t* og = act + RB_O + hf * 14336 + (7 * j + 3 * w) * 256 + wi * 64 + lane;
#pragma unroll
                    for (int g = 0; g < 4; g++) {
                        if ((g == 3 - 3 * w) ? ((q >> 1) == w) : true) {
                            og[g * 256] = pack2(o[4 * g] * ia, o[4 * g + 1] * ia);
                            og[g * 256 + 32] = pack2(o[4 * g + 2] * ib, o[4 * g + 3] * ib);
                        }
                    }
                    warp_arrive(BAR(B_PUB + 2 + hf));
                    PROFC(10 + 3 * hf);
                }
            }
        }
        uint32_t x1p[14];
        COORDS
        constexpr uint64_t DT = dconst(1024, 128, 0);
        const int tile = opaque((lds1(sb + M_EPOCH) & 1) * 2 + w);
        if (RUN(4)) {
            float ac[28];
            const uint32_t ad = mkdesc(sb + (w ? OFF_Y + HALF : OFF_X), DT), bd = mkdesc(sb + OFF_X + HALF, DB128) + kh;
            WAIT(B_WOFULL, 0);
            WAIT(B_MOD2, 0);
            WAIT(B_GFULL + w, 0);
            PROFC(28);
            reg_def<28>(ac);
#pragma unroll 1
            for (int u = 0; u < 4; u++) {
                if (u == 2) WAIT(B_XFULL + 2 + w, 1);
                WG_FENCE();
#pragma unroll
                for (int i = 0; i < 7; i++) wgmma_ss_56<DT, DB128>(ac, ad + (7 * u + i) * 128, bd + (7 * u + i) * 128, (u | i) != 0);
            }
            WG_COMMIT();
            WG_WAIT(0);
            reg_fence<28>(ac);
            PROFC(14);
            __syncwarp();
            if (lane < 4) mbar_arrive(BAR(B_EMPTY + 3 + lane));
            if (lane < 3 && w == 0) mbar_arrive(BAR(B_EMPTY + lane));
            float s1a = 0.f, s2a = 0.f, s1b = 0.f, s2b = 0.f;
            uint32_t* xo = act + RB_X1 + tile * 14336 + 7 * j * 256 + wi * 64 + lane;
#pragma unroll
            for (int g = 0; g < 7; g++) {
                const float2 ga = *(const float2*)(smem + M_G + (8 * g + 2 * q) * 4);
                x1p[2 * g] = pack2(fmaf(ga.x, ac[4 * g], bf_lo(xr[2 * g])), fmaf(ga.y, ac[4 * g + 1], bf_hi(xr[2 * g])));
                x1p[2 * g + 1] = pack2(fmaf(ga.x, ac[4 * g + 2], bf_lo(xr[2 * g + 1])), fmaf(ga.y, ac[4 * g + 3], bf_hi(xr[2 * g + 1])));
                st_relaxed(xo + g * 256, max(x1p[2 * g], 1u)); st_relaxed(xo + g * 256 + 32, max(x1p[2 * g + 1], 1u));
                const float u0 = bf_lo(x1p[2 * g]), u1 = bf_hi(x1p[2 * g]), u2 = bf_lo(x1p[2 * g + 1]), u3 = bf_hi(x1p[2 * g + 1]);
                s1a += u0 + u1; s2a += u0 * u0 + u1 * u1; s1b += u2 + u3; s2b += u2 * u2 + u3 * u3;
            }
            float ka = (q & 1) ? s2a : s1a, kb2 = (q & 1) ? s2b : s1b;
            ka += __shfl_xor_sync(~0u, (q & 1) ? s1a : s2a, 1); kb2 += __shfl_xor_sync(~0u, (q & 1) ? s1b : s2b, 1);
            const float kk = ((q & 2) ? kb2 : ka) + __shfl_xor_sync(~0u, (q & 2) ? ka : kb2, 2);
            st_relaxed(act + RB_ST + ((tile * 8 + j) * 64 + 16 * wi + lr + 4 * (q & 2)) * 2 + (q & 1), max(__float_as_uint(kk), 1u));
            __syncwarp();
            if (lane < 2) mbar_arrive(BAR(B_PUB + 4 + w));
        } else reg_def<14>(x1p);
        PROFC(15);
        uint32_t h2a[32], h2b[24];
        {
            const int fa = pass_f(fs, 0), fb = pass_f(fs, 1), fc = pass_f(fs, 2);
            uint32_t* h2g = act + RB_H2 + (8 * w + 2 * wi) * 32 + lane;
            const uint32_t a0 = mkdesc(sb + OFF_Y + w * HALF, DT);
            if (RUN(3)) {
                uint32_t ra2, na2, rb2, nb2;
                {
                    const uint32_t* sg = act + RB_ST + ((tile * 8 + 2 * q) * 64 + 16 * wi + lr) * 2;
                    uint2 u[4];
                    do {
#pragma unroll
                        for (int i = 0; i < 4; i++) u[i] = ld_relaxed2(sg + (i >> 1) * 128 + (i & 1) * 16);
                    } while (__any_sync(~0u, min(min(min(u[0].x, u[0].y), min(u[1].x, u[1].y)), min(min(u[2].x, u[2].y), min(u[3].x, u[3].y))) == 0u) && !sc);
                    float v[4] = {__uint_as_float(u[0].x) + __uint_as_float(u[2].x), __uint_as_float(u[0].y) + __uint_as_float(u[2].y),
                                  __uint_as_float(u[1].x) + __uint_as_float(u[3].x), __uint_as_float(u[1].y) + __uint_as_float(u[3].y)};
#pragma unroll
                    for (int i = 0; i < 4; i++) { v[i] += __shfl_xor_sync(~0u, v[i], 1); v[i] += __shfl_xor_sync(~0u, v[i], 2); }
                    ln_coeffs(v[0] * (1.f / DM), v[1] * (1.f / DM), ra2, na2);
                    ln_coeffs(v[2] * (1.f / DM), v[3] * (1.f / DM), rb2, nb2);
                }
                WAIT(B_GFULL + 2 + w, 0);
                PROFC(16);
                const uint32_t ha = sb + OFF_Y + w * HALF + (lane >> 4) * 1024 + (2 * wi + ((lane >> 3) & 1)) * 128 + (lane & 7) * 16;
                const uint32_t sta = sb + M_ST + q * 16;
                const uint32_t* xg = act + RB_X1 + tile * 14336 + wi * 64 + lane;
                uint32_t x[8];
                uint4 st[2];
                uint32_t hl = ha, sl2 = sta;
                auto load = [&]() {
                    ldsm4(hl, x); ldsm4(hl + 2048, x + 4);
                    st[0] = lds4(sl2); st[1] = lds4(sl2 + 64);
                };
                float ac[128];
                uint32_t ad = a0 - 256, bd = mkdesc(sb, DB128) - 1024, fb_ = BAR(B_FULL - 1), eb_ = BAR(B_DUMMY), par = sc;
                reg_def<128>(ac);
                load();
#pragma unroll 1
                for (int s = -1; s < 14; s++) {
                    if (s >= 0) {
                        mbar_wait_c(fb_, par);
                        WG_FENCE();
                        wgmma_ss_256<DT, DB128>(ac, ad, bd, s != 0);
                        wgmma_ss_256<DT, DB128>(ac, ad + 128, bd + 128, 1);
                        WG_COMMIT();
                    }
                    if (s < 13) {
                        if (__any_sync(~0u, min(min(min(x[0], x[1]), min(x[2], x[3])), min(min(x[4], x[5]), min(x[6], x[7]))) < 1u - sc)) x1_fix(x, xg + ((hl - ha) >> 2));
#pragma unroll
                        for (int i = 0; i < 2; i++)
                            stsm4(hl + 2048 * i, hfma2(hfma2(x[4 * i], ra2, na2), st[i].x, st[i].y), hfma2(hfma2(x[4 * i + 1], rb2, nb2), st[i].x, st[i].y),
                                  hfma2(hfma2(x[4 * i + 2], ra2, na2), st[i].z, st[i].w), hfma2(hfma2(x[4 * i + 3], rb2, nb2), st[i].z, st[i].w));
                        fence_async_smem();
                        if (s == 3) mbar_wait_c(BAR(B_XFULL + 4 + w), 1);
                        if (s < 12) { hl += 4096; sl2 += 128; }
                        load();
                    }
                    WG_WAIT(1);
                    warp_arrive(eb_);
                    if (s >= 0) eb_ = fb_ + 8 * (B_EMPTY - B_FULL);
                    ad += 256; bd += 1024; fb_ += 8;
                    if (s == 6) { bd -= 7 * 1024; fb_ -= 56; par = 1; }
                }
                PROFC(18);
                WG_WAIT(0);
                reg_fence<128>(ac);
                warp_arrive(BAR(B_EMPTY + 6));
#pragma unroll
                for (int g = 0; g < 16; g++) {
                    h2a[2 * g] = hmul2(pack2_relu(ac[4 * g], ac[4 * g + 1]), pack2(ac[64 + 4 * g], ac[64 + 4 * g + 1]));
                    h2a[2 * g + 1] = hmul2(pack2_relu(ac[4 * g + 2], ac[4 * g + 3]), pack2(ac[64 + 4 * g + 2], ac[64 + 4 * g + 3]));
                    h2g[(fa / 8 + g) * 512] = h2a[2 * g]; h2g[(fa / 8 + g) * 512 + 32] = h2a[2 * g + 1];
                }
                warp_arrive(BAR(B_PUB + 6));
            } else reg_def<32>(h2a);
            PROFC(19);
            if (RUN(5)) {
                float ac[64];
                reg_def<64>(ac);
                const uint32_t bx = mkdesc(sb, dconst(8192, 1024, 1));
#pragma unroll kB
                for (int s = 0; s < 7; s++) {
                    WAIT(B_FULL + s, 0);
                    const uint32_t ad = a0 + s * 512, bd = bx + (slot_off(s) >> 4);
                    WG_FENCE();
#pragma unroll
                    for (int k = 0; k < 4; k++) wgmma_ss_128<DT, DB128>(ac, ad + k * 128, bd + k * 128, (s | k) != 0);
                    WG_COMMIT();
                    if (s > 0) { WG_WAIT(1); warp_arrive(BAR(B_EMPTY + s - 1)); }
                }
                WG_WAIT(0);
                reg_fence<64>(ac);
                warp_arrive(BAR(B_EMPTY + 6));
#pragma unroll
                for (int g = 0; g < 8; g++) {
                    h2b[2 * g] = hmul2(pack2_relu(ac[4 * g], ac[4 * g + 1]), pack2(ac[32 + 4 * g], ac[32 + 4 * g + 1]));
                    h2b[2 * g + 1] = hmul2(pack2_relu(ac[4 * g + 2], ac[4 * g + 3]), pack2(ac[32 + 4 * g + 2], ac[32 + 4 * g + 3]));
                    h2g[(fb / 8 + g) * 512] = h2b[2 * g]; h2g[(fb / 8 + g) * 512 + 32] = h2b[2 * g + 1];
                }
                warp_arrive(BAR(B_PUB + 7));
            } else reg_def<16>(h2b);
            PROFC(27);
            if (RUN(6)) {
                float ac[32];
                reg_def<32>(ac);
                const uint32_t bx = mkdesc(sb, dconst(4096, 512, 2));
#pragma unroll kC
                for (int s = 0; s < 7; s++) {
                    WAIT(B_FULL + s, 1);
                    const uint32_t ad = a0 + s * 512, bd = bx + (slot_off(s) >> 4);
                    WG_FENCE();
#pragma unroll
                    for (int k = 0; k < 4; k++) wgmma_ss_64<DT, dconst(4096, 512, 2)>(ac, ad + k * 128, bd + k * 64, (s | k) != 0);
                    WG_COMMIT();
                    if (s > 0) { WG_WAIT(1); warp_arrive(BAR(B_EMPTY + s - 1)); }
                }
                WG_WAIT(0);
                reg_fence<32>(ac);
                __syncwarp();
                if (lane < 6) mbar_arrive(BAR(B_EMPTY + 6 + lane));
                PROFC(20);
#pragma unroll
                for (int g = 0; g < 4; g++) {
                    h2b[16 + 2 * g] = hmul2(pack2_relu(ac[4 * g], ac[4 * g + 1]), pack2(ac[16 + 4 * g], ac[16 + 4 * g + 1]));
                    h2b[16 + 2 * g + 1] = hmul2(pack2_relu(ac[4 * g + 2], ac[4 * g + 3]), pack2(ac[16 + 4 * g + 2], ac[16 + 4 * g + 3]));
                    h2g[(fc / 8 + g) * 512] = h2b[16 + 2 * g]; h2g[(fc / 8 + g) * 512 + 32] = h2b[16 + 2 * g + 1];
                }
                warp_arrive(BAR(B_PUB + 8));
                asm volatile("barrier.cluster.wait.aligned;" ::: "memory");
                if (lane == 0 && !sc) {
                    uint32_t rb;
                    asm volatile("mapa.shared::cluster.u32 %0, %1, %2;" : "=r"(rb) : "r"(BAR(B_PEER)), "r"(kh ^ 1));
                    asm volatile("mbarrier.arrive.relaxed.cluster.shared::cluster.b64 _, [%0];" ::"r"(rb) : "memory");
                }
            } else reg_def<8>(h2b + 16);
        }
        PROFC(21);
        if (RUN(7)) {
            float ac[56];
            reg_def<56>(ac);
            constexpr uint64_t DAN = dconst(2048, 128, 0);
            constexpr uint64_t DW = dconst(128, 512, 0);
            const uint32_t bx = mkdesc(sb, DW);
#pragma unroll
            for (int e = 0; e < 4; e++) {
                WAIT(B_FULL + e, 0);
                const uint32_t bd = bx + (slot_off(e) >> 4);
                const uint32_t* hh = e < 2 ? h2a + 16 * e : h2b + 16 * (e - 2);
                WG_FENCE();
#pragma unroll
                for (int k = 0; k < (e < 3 ? 4 : 2); k++) wgmma_rs_112<DW>(ac, hh[4 * k], hh[4 * k + 1], hh[4 * k + 2], hh[4 * k + 3], bd + (k >> 1) * 512 + (k & 1) * 16, (e | k) != 0);
                WG_COMMIT();
                if (e > 0) { WG_WAIT(1); warp_arrive(BAR(B_EMPTY + e - 1)); }
            }
            PROFC(22);
            uint32_t ad = mkdesc(sb + 4 * 16384 + 8192 + w * 1024, DAN), bd = bx + 4 * 1024, fb_ = BAR(B_FULL + 4), eb_ = BAR(B_EMPTY + 3), par = sc;
#pragma unroll 1
            for (int e = 4; e < 25; e++) {
                mbar_wait_c(fb_, par);
                WG_FENCE();
                wgmma_ss_112<DAN, DW>(ac, ad, bd, 1);
                wgmma_ss_112<DAN, DW>(ac, ad + 256, bd + 16, 1);
                WG_COMMIT();
                WG_WAIT(1);
                warp_arrive(eb_);
                eb_ = fb_ + 8 * (B_EMPTY - B_FULL);
                ad += 1024; bd += 1024; fb_ += 8;
                if (e == 11 || e == 23) { ad -= 12 * 1024; bd -= 12 * 1024; fb_ -= 96; par = (par ^ 1) | sc; }
            }
            mbar_wait_cluster(BAR(B_PEER), sc);
            WG_WAIT(0);
            reg_fence<56>(ac);
            PROFC(24);
            uint32_t rdst, rbar;
            asm volatile("mapa.shared::cluster.u32 %0, %1, %2;" : "=r"(rdst) : "r"(sb + OFF_Y + (5 + w) * 16384 + t * 16), "r"(kh ^ 1 ^ sc));
            asm volatile("mapa.shared::cluster.u32 %0, %1, %2;" : "=r"(rbar) : "r"(BAR(B_XCH + w)), "r"(kh ^ 1 ^ sc));
#define ACG(g, i) ac[4 * (g) + (i)]
#pragma unroll
            for (int g = 0; g < 7; g++) {
                const float v0 = kh ? ACG(g, 0) : ACG(g + 7, 0), v1 = kh ? ACG(g, 1) : ACG(g + 7, 1);
                const float v2 = kh ? ACG(g, 2) : ACG(g + 7, 2), v3 = kh ? ACG(g, 3) : ACG(g + 7, 3);
                if (!sc) asm volatile("st.async.shared::cluster.mbarrier::complete_tx::bytes.v4.f32 [%0], {%1,%2,%3,%4}, [%5];"
                             ::"r"(rdst + g * 2048), "f"(v0), "f"(v1), "f"(v2), "f"(v3), "r"(rbar) : "memory");
            }
            mbar_wait_cluster(BAR(B_XCH + w), sc);
            PROFC(25);
            bf16* og = (sc ? (bf16*)act : p.out + (size_t)128 * r * DM) + (size_t)ra * DM + 56 * j + 2 * q;
#pragma unroll
            for (int g = 0; g < 7; g++) {
                const uint4 rv = *(const uint4*)(smem + OFF_Y + (5 + w) * 16384 + t * 16 + g * 2048);
                const float2 gb = *(const float2*)(smem + M_G + 224 + (8 * g + 2 * q) * 4);
                const float v0 = (kh ? ACG(g + 7, 0) : ACG(g, 0)) + __uint_as_float(rv.x), v1 = (kh ? ACG(g + 7, 1) : ACG(g, 1)) + __uint_as_float(rv.y);
                const float v2 = (kh ? ACG(g + 7, 2) : ACG(g, 2)) + __uint_as_float(rv.z), v3 = (kh ? ACG(g + 7, 3) : ACG(g, 3)) + __uint_as_float(rv.w);
                *(uint32_t*)(og + 8 * g) = pack2(fmaf(gb.x, v0, bf_lo(x1p[2 * g])), fmaf(gb.y, v1, bf_hi(x1p[2 * g])));
                *(uint32_t*)(og + 8 * DM + 8 * g) = pack2(fmaf(gb.x, v2, bf_lo(x1p[2 * g + 1])), fmaf(gb.y, v3, bf_hi(x1p[2 * g + 1])));
            }
        }
        PROFC(26);
        bar_sync(1 + w, 128);
        if (wi == 0) warp_arrive(BAR(B_DONE));
    } else {
        const int lane = fresh_tid() & 31;
        const bool early = kh == 0, gemv = r < 14;
        const int mcol = early ? 16 * (4 * r + nq) : 2 * DM + 32 * (4 * r + nq);
        const uint32_t wmbuf = sb + OFF_Y + HALF;
        asm volatile("setmaxnreg.dec.sync.aligned.u32 56;");
        if (warp == 9) {
#pragma unroll
            for (int i = 56; i < 64; i++) init_e(BAR(i), 1);
            fence_async_smem();
        }
        if (warp == 8) { init_e(BAR(B_WMFULL), 2); fence_async_smem(); }
        bar_arrive(0, 384);
        asm volatile("barrier.cluster.arrive.relaxed.aligned;" ::: "memory");
        uint32_t target = 0;
        if (warp == 8) {
            if (!sc) {
                expect_e(BAR(B_WMFULL), gemv ? 28672 >> early : 0);
                if (early && gemv) { tma3_e(wmbuf, &p.wm, mcol, 0, 0, BAR(B_WMFULL)); tma3_e(wmbuf + 7168, &p.wm, mcol, 224, 0, BAR(B_WMFULL)); }
#pragma unroll 1
                for (int kb = 0; kb < 7; kb++) {
                    expect_e(BAR(B_XFULL + kb), 16384);
                    tma3_e(sb + OFF_X + kb * 16384, &p.xm, 64 * kb, 128 * r, 0, BAR(B_XFULL + kb));
                }
            }
#pragma unroll 1
            for (int mt = 0; mt < 4; mt++) {
                if (mt == 1) {
                    if (!early && gemv) {
#pragma unroll 1
                        for (int k = 0; k < 4; k++) tma3_e(wmbuf + k * 7168, &p.wm, mcol + (k >> 1) * 16, (k & 1) * 224, 0, BAR(B_WMFULL));
                    }
                    bar_sync(9, 384);
                    if (sc) return;
                    mbar_wait(BAR(B_MOD1), 0);
                    mbar_wait(BAR(B_WMFREE), 0);
                }
                if (mt == 2) mbar_wait(BAR(B_XFREE), 0);
                if (mt == 3) mbar_wait(BAR(B_VRFULL), 0);
                const uint32_t bar = BAR(mt == 3 ? B_WOFULL : B_FULLK + mt), dst = sb + (mt < 2 ? OFF_Y : OFF_X) + (mt & 1) * HALF;
                const int c0 = (mt < 2 ? DM + DM * mt : 0) + 56 * j - 8 * kh;
                if (!sc) {
                    expect_e(bar, HALF);
                    tma3_e(dst, mt == 3 ? &p.wo : &p.qkv, c0, 0, 0, bar);
                    tma3_e(dst + HALF / 2, mt == 3 ? &p.wo : &p.qkv, c0, 224, 0, bar);
                }
            }
            expect_e(BAR(B_XCH), 14336);
            expect_e(BAR(B_XCH + 1), 14336);
        } else {
            if (warp == 10 && !sc) {
                l2_prefetch_e((const char*)p.wqkv + (size_t)b * 9408, 9408);
                if (lane == 0) sts1(sb + M_EPOCH, atomicAdd(&g_ticket, 1u) / NCTA);
            }
            if (warp == 11) {
#pragma unroll
                for (int i = 0; i < 8; i++) {
                    const int wd = lane + 32 * i;
                    const uint32_t cb = i < 7 ? __ldg((const uint32_t*)p.c + wd) : 0u;
                    sts1(wmbuf + 28672 + (wd >> 3) * 32 + (wd & 3) * 8 + (wd & 4), pack2(silu_bf(cb & 0xFFFFu), silu_bf(cb >> 16)));
                }
            }
            bar_sync(9, 384);
            if (sc) return;
            target = lds1(sb + M_EPOCH) + 1;
            const uint32_t tag = target & 0xFFFFu;
            if (warp == 11) {
                warp_arrive(BAR(B_WMFULL));
                mbar_wait(BAR(B_GEMV), 0);
                float sum = 0.f;
#pragma unroll
                for (int i = 0; i < 8; i++) sum += *(const float*)(smem + OFF_Y + HALF + 29696 + (i * 32 + (early ? lane & 15 : lane)) * 4);
                const uint32_t word = (pack2(sum, 0.f) << 16) | tag;
                if (gemv) {
                    uint32_t* mg = g_mod + mcol + (early ? (lane & 15) + (lane >> 4) * 4 * 6 * DM : lane);
#pragma unroll
                    for (int i = 0; i < 8; i++) if (i < 4 || !early) st_relaxed(mg + i * 6 * DM, word);
                }
                warp_arrive(BAR(B_WMFREE));
            }
            const uint4* modp = (const uint4*)g_mod + (r & 7) * (6 * DM / 4);
            const bool p2 = warp == 11;
            mbar_wait(BAR(p2 ? B_PUB : B_XFULL + 4), 0);
#pragma unroll 1
            for (int it = p2 ? 0 : warp - 9; it < (p2 ? 2 : warp - 8); it++) {
                const int i0 = lane + 32 * it, imax = p2 ? 251 : 223;
                uint4 v[4];
#pragma unroll 1
                for (int n = 0;; n++) {
                    uint32_t bad = 0;
#pragma unroll
                    for (int k = 0; k < 4; k++) {
                        const int i = min(i0 + 64 * k, imax);
                        v[k] = ld_relaxed4(modp + (i < 224 ? (p2 ? 336 : 0) + i : (i < 238 ? 14 * j + i : 14 * j + i + 322)));
                        bad |= (v[k].x ^ tag) | (v[k].y ^ tag) | (v[k].z ^ tag) | (v[k].w ^ tag);
                    }
                    if (!__any_sync(~0u, bad & 0xFFFFu)) break;
                    if (n > SPIN_LIMIT) __trap();
                }
#pragma unroll
                for (int k = 0; k < 4; k++) {
                    const int i = min(i0 + 64 * k, imax);
                    if (i < 224) {
                        const int isc = i >= 112, c4 = i - 112 * isc;
                        const float one = isc ? 1.f : 0.f;
                        const uint32_t a = sb + M_ST + (c4 >> 2) * 64 + (c4 & 1) * 32 + (c4 & 2) * 4 + (isc ? 0 : 4);
                        sts1(a, pack2(bf_hi(v[k].x) + one, bf_hi(v[k].y) + one));
                        sts1(a + 16, pack2(bf_hi(v[k].z) + one, bf_hi(v[k].w) + one));
                    } else {
                        sts4(sb + M_G + (i - 224) * 16, make_uint4(v[k].x & 0xFFFF0000u, v[k].y & 0xFFFF0000u, v[k].z & 0xFFFF0000u, v[k].w & 0xFFFF0000u));
                    }
                }
                warp_arrive(BAR(p2 ? B_MOD2 : B_MOD1));
            }
            if (warp == 9) {
#pragma unroll 1
                for (int kv = 0; kv < 2; kv++) {
                    mbar_wait(BAR(B_PUB + kv), 0);
                    wait_flags(g_flag + b * 128 + lane, target, (r >= 2 ? 6u : r == 1 ? 2u : 0u) << (8 * kv));
                    fence_async_global();
                    const uint32_t dst = sb + OFF_Y + (kv ? Y_VR : Y_K);
                    expect_e(BAR(B_KRFULL + kv), r >= 2 ? 28672 : r == 1 ? 14336 : 0);
                    if (r >= 2) bulk_e(dst, act - 2 * RB_WORDS + RB_KV + j * 7168 + kv * 3584, 14336, BAR(B_KRFULL + kv));
                    if (r >= 1) bulk_e(dst + 14336, act - RB_WORDS + RB_KV + j * 7168 + kv * 3584, 14336, BAR(B_KRFULL + kv));
                }
            } else if (warp == 11) {
                mbar_wait(BAR(B_VRFULL), 0);
                l2_prefetch_e((const char*)p.wg + (size_t)b * 12544, 12544);
                l2_prefetch_e((const char*)p.wu + (size_t)b * 12544, 12544);
#pragma unroll 1
                for (int k = 0; k < (r < 12 ? 2 : 1); k++) {
                    const int u = 28 * kh + r + 16 * k;
                    expect_e(BAR(B_XFULL + k), 7168);
                    tma3_e(sb + OFF_Y + 102400, &p.dn, 0, 32 * u, 14 * nq, BAR(B_XFULL + k));
                    mbar_wait(BAR(B_XFULL + k), 1);
                    asm volatile("{\n.reg .pred p;\nelect.sync _|p, 0xffffffff;\n@p cp.async.bulk.global.shared::cta.bulk_group [%0], [%1], 7168;\n"
                                 "cp.async.bulk.commit_group;\ncp.async.bulk.wait_group 0;\n}" ::"l"(g_wd + (size_t)(u * 4 + nq) * 1792), "r"(sb + OFF_Y + 102400) : "memory");
                    __syncwarp();
                }
                warp_arrive(BAR(B_WMFREE));
                fence_gpu();
                if (lane < 16) st_relaxed(g_flag + (8 * lane + j) * 128 + 96 + r, target);
            }
        }
        if (warp == 8 || warp == 11) {
            const int sec = warp == 11;
            if (sec) ring_loader<1>(p, sb, r, j, lane); else ring_loader<0>(p, sb, r, j, lane);
            mbar_wait(BAR(B_DONE), 0);
        } else if (warp == 9) {
#pragma unroll
            for (int ev = 0; ev < 4; ev++) { expect_e(BAR(B_GFULL + ev), ev < 2 ? HALF / 2 : 20480); expect_e(BAR(B_XFULL + 2 + ev), ev < 2 ? HALF / 2 : HALF - 20480); }
            mbar_wait(BAR(B_PUB + 2), 0);
            const uint32_t* fp = g_flag + b * 128 + 32 + lane;
            const int par = (target - 1) & 1;
#pragma unroll 1
            for (int n = 0, ev = 0; ev < 4; n++) {
                if (ev == 1) { mbar_wait(BAR(B_WMFREE), 1); mbar_wait(BAR(B_PUB + 3), 0); }
                uint32_t ok = __ballot_sync(~0u, (int)(ld_relaxed(fp) - target) >= 0) >> (8 * ev);
                while ((ok & 0xFFu) == 0xFFu) {
                    asm volatile("fence.acquire.gpu;" ::: "memory");
                    fence_async_global();
                    const int tile = (ev & 1) + (ev >> 1) * par * 2;
                    const uint32_t dst = sb + (ev == 0 ? OFF_X : OFF_Y + (ev & 1) * HALF), first = ev < 2 ? HALF / 2 : 20480;
                    const char* src = (const char*)(act + RB_O + ((ev >> 1) * 2 + tile) * 14336);
                    bulk_e(dst, src, first, BAR(B_GFULL + ev));
                    bulk_e(dst + first, src + first, HALF - first, BAR(B_XFULL + 2 + ev));
                    if (ev) PROFH(4 + ev);
                    ev++; ok >>= 8;
                }
                if (n > SPIN_LIMIT) __trap();
            }
            mbar_wait(BAR(B_XFULL + 5), 1);
#pragma unroll 1
            for (int hf = 0; hf < 2; hf++) {
                const int tile = (par ^ 1) * 2 + hf;
                uint4* xz = (uint4*)(act + RB_X1 + tile * 14336 + j * 1792) + lane;
#pragma unroll
                for (int i = 0; i < 14; i++) xz[i * 32] = make_uint4(0, 0, 0, 0);
                ((uint4*)(act + RB_ST + (tile * 8 + j) * 128))[lane] = make_uint4(0, 0, 0, 0);
            }
#pragma unroll 1
            for (int ps = 0; ps < 3; ps++) {
                mbar_wait(BAR(B_PUB + 6 + ps), 0);
                wait_flags(g_flag + b * 128 + 64 + lane, target, (0x55u << kh) << (8 * ps));
                warp_arrive(BAR(B_HRDY + ps));
                PROFH(9 + ps);
            }
        } else {
#pragma unroll 1
            for (int k = 0; k < 9; k++) {
                uint32_t* fp = k < 2 ? g_flag + (b + 8 * lane) * 128 + k * 8 + lane : g_flag + (8 * r + lane) * 128 + 16 + k * 8 + j;
                mbar_wait(BAR(B_PUB + k), 0);
                if (k != 4 && k != 5) fence_gpu();
                if (k < 2 ? (lane == 1 || lane == 2) : lane < 8) st_relaxed(fp, target);
                if (k >= 3 && k <= 5) PROFH(k - 3);
            }
        }
    }
}

#undef act
typedef CUresult (*EncodeFn)(CUtensorMap*, CUtensorMapDataType, cuuint32_t, void*, const cuuint64_t*, const cuuint64_t*, const cuuint32_t*,
                             const cuuint32_t*, CUtensorMapInterleave, CUtensorMapSwizzle, CUtensorMapL2promotion, CUtensorMapFloatOOBfill);

static void make_map(EncodeFn fn, CUtensorMap* m, const void* ptr, uint64_t d0, uint64_t d1, uint64_t d2, uint64_t s1, uint64_t s2,
                     uint32_t b0, uint32_t b1, uint32_t b2, CUtensorMapSwizzle sw) {
    cuuint64_t dims[3] = {d0, d1, d2}, strides[2] = {s1, s2};
    cuuint32_t box[3] = {b0, b1, b2}, es[3] = {1, 1, 1};
    CUresult rc = fn(m, CU_TENSOR_MAP_DATA_TYPE_BFLOAT16, 3, (void*)ptr, dims, strides, box, es, CU_TENSOR_MAP_INTERLEAVE_NONE, sw,
                     CU_TENSOR_MAP_L2_PROMOTION_L2_128B, CU_TENSOR_MAP_FLOAT_OOB_FILL_NONE);
    (void)rc;
}

extern "C" void kernel_launch(void* const* d_in, const int* in_sizes, int n_in, void* d_out, int out_size) {
    (void)in_sizes; (void)n_in; (void)out_size;
    static EncodeFn fn = nullptr;
    static uint32_t* act_base = nullptr;
    if (!fn) {
        cudaDriverEntryPointQueryResult st;
        cudaGetDriverEntryPoint("cuTensorMapEncodeTiled", (void**)&fn, cudaEnableDefault, &st);
        void* a = nullptr;
        cudaGetSymbolAddress(&a, g_act);
        act_base = (uint32_t*)(((uintptr_t)a + 0xFFFFF) & ~(uintptr_t)0xFFFFF);
        cudaFuncSetAttribute(fused_block_kernel, cudaFuncAttributeMaxDynamicSharedMemorySize, SMEM_BYTES);
    }
    Params p;
    p.x = (const bf16*)d_in[0];
    const bf16* wqkv = (const bf16*)d_in[1];
    p.wqkv = wqkv;
    p.wop = (const bf16*)d_in[2];
    p.wg = (const bf16*)d_in[4];
    p.wu = (const bf16*)d_in[5];
    p.wd = (const bf16*)d_in[6];
    p.c = (const bf16*)d_in[7];
    p.wmod = (const bf16*)d_in[8];
    p.out = (bf16*)d_out;
    p.zero = 0;
    p.actb = act_base;
    make_map(fn, &p.wm, p.wmod, 2688, 448, 1, 5376, 5376 * 448, 16, 224, 1, CU_TENSOR_MAP_SWIZZLE_NONE);
    make_map(fn, &p.xm, p.x, 448, 2048, 1, 896, 896 * 2048, 64, 128, 1, CU_TENSOR_MAP_SWIZZLE_128B);
    make_map(fn, &p.qkv, wqkv, 1344, 448, 1, 2688, 2688 * 448, 64, 224, 1, CU_TENSOR_MAP_SWIZZLE_128B);
    make_map(fn, &p.wo, p.wop, 448, 448, 1, 896, 896 * 448, 64, 224, 1, CU_TENSOR_MAP_SWIZZLE_128B);
    make_map(fn, &p.ga, p.wg, 64, 448, 28, 3584, 128, 64, 32, 2, CU_TENSOR_MAP_SWIZZLE_128B);
    make_map(fn, &p.ua, p.wu, 64, 448, 28, 3584, 128, 64, 32, 2, CU_TENSOR_MAP_SWIZZLE_128B);
    make_map(fn, &p.gb, p.wg, 64, 448, 28, 3584, 128, 64, 64, 1, CU_TENSOR_MAP_SWIZZLE_128B);
    make_map(fn, &p.ub, p.wu, 64, 448, 28, 3584, 128, 64, 64, 1, CU_TENSOR_MAP_SWIZZLE_128B);
    make_map(fn, &p.gc, p.wg, 32, 448, 56, 3584, 64, 32, 64, 1, CU_TENSOR_MAP_SWIZZLE_64B);
    make_map(fn, &p.uc, p.wu, 32, 448, 56, 3584, 64, 32, 64, 1, CU_TENSOR_MAP_SWIZZLE_64B);
    make_map(fn, &p.dn, p.wd, 8, 1792, 56, 896, 16, 8, 32, 14, CU_TENSOR_MAP_SWIZZLE_NONE);
    fused_block_kernel<<<GRID, 384, SMEM_BYTES>>>(p);
}
```

```cpp
#include <cuda_runtime.h>
#include <cuda_bf16.h>
#include <cuda.h>
#include <stdint.h>

typedef __nv_bfloat16 bf16;

template<uint64_t CB> __device__ __forceinline__ void wgmma_rs_56(float* d, uint32_t a0, uint32_t a1, uint32_t a2, uint32_t a3, uint32_t db, int sd) {
  asm volatile("{\n.reg .pred p;\n.reg .b64 b;\nsetp.ne.b32 p, %33, 0;\nmov.b64 b, {%32, %34};\n"
    "wgmma.mma_async.sync.aligned.m64n56k16.f32.bf16.bf16 {%0,%1,%2,%3,%4,%5,%6,%7,%8,%9,%10,%11,%12,%13,%14,%15,%16,%17,%18,%19,%20,%21,%22,%23,%24,%25,%26,%27}, {%28,%29,%30,%31}, b, p, 1, 1, 1;\n}\n"
    : "+f"(d[0]),"+f"(d[1]),"+f"(d[2]),"+f"(d[3]),"+f"(d[4]),"+f"(d[5]),"+f"(d[6]),"+f"(d[7]),"+f"(d[8]),"+f"(d[9]),"+f"(d[10]),"+f"(d[11]),"+f"(d[12]),"+f"(d[13]),"+f"(d[14]),"+f"(d[15]),"+f"(d[16]),"+f"(d[17]),"+f"(d[18]),"+f"(d[19]),"+f"(d[20]),"+f"(d[21]),"+f"(d[22]),"+f"(d[23]),"+f"(d[24]),"+f"(d[25]),"+f"(d[26]),"+f"(d[27])
    : "r"(a0), "r"(a1), "r"(a2), "r"(a3), "r"(db), "r"(sd), "n"((uint32_t)(CB >> 32)));
}
template<uint64_t CA, uint64_t CB> __device__ __forceinline__ void wgmma_ss_56(float* d, uint32_t da, uint32_t db, int sd) {
  asm volatile("{\n.reg .pred p;\n.reg .b64 a, b;\nsetp.ne.b32 p, %30, 0;\nmov.b64 a, {%28, %31};\nmov.b64 b, {%29, %32};\n"
    "wgmma.mma_async.sync.aligned.m64n56k16.f32.bf16.bf16 {%0,%1,%2,%3,%4,%5,%6,%7,%8,%9,%10,%11,%12,%13,%14,%15,%16,%17,%18,%19,%20,%21,%22,%23,%24,%25,%26,%27}, a, b, p, 1, 1, 0, 1;\n}\n"
    : "+f"(d[0]),"+f"(d[1]),"+f"(d[2]),"+f"(d[3]),"+f"(d[4]),"+f"(d[5]),"+f"(d[6]),"+f"(d[7]),"+f"(d[8]),"+f"(d[9]),"+f"(d[10]),"+f"(d[11]),"+f"(d[12]),"+f"(d[13]),"+f"(d[14]),"+f"(d[15]),"+f"(d[16]),"+f"(d[17]),"+f"(d[18]),"+f"(d[19]),"+f"(d[20]),"+f"(d[21]),"+f"(d[22]),"+f"(d[23]),"+f"(d[24]),"+f"(d[25]),"+f"(d[26]),"+f"(d[27])
    : "r"(da), "r"(db), "r"(sd), "n"((uint32_t)(CA >> 32)), "n"((uint32_t)(CB >> 32)));
}
template<uint64_t CA, uint64_t CB> __device__ __forceinline__ void wgmma_ss_256(float* d, uint32_t da, uint32_t db, int sd) {
  asm volatile("{\n.reg .pred p;\n.reg .b64 a, b;\nsetp.ne.b32 p, %130, 0;\nmov.b64 a, {%128, %131};\nmov.b64 b, {%129, %132};\n"
    "wgmma.mma_async.sync.aligned.m64n256k16.f32.bf16.bf16 {%0,%1,%2,%3,%4,%5,%6,%7,%8,%9,%10,%11,%12,%13,%14,%15,%16,%17,%18,%19,%20,%21,%22,%23,%24,%25,%26,%27,%28,%29,%30,%31,%32,%33,%34,%35,%36,%37,%38,%39,%40,%41,%42,%43,%44,%45,%46,%47,%48,%49,%50,%51,%52,%53,%54,%55,%56,%57,%58,%59,%60,%61,%62,%63,%64,%65,%66,%67,%68,%69,%70,%71,%72,%73,%74,%75,%76,%77,%78,%79,%80,%81,%82,%83,%84,%85,%86,%87,%88,%89,%90,%91,%92,%93,%94,%95,%96,%97,%98,%99,%100,%101,%102,%103,%104,%105,%106,%107,%108,%109,%110,%111,%112,%113,%114,%115,%116,%117,%118,%119,%120,%121,%122,%123,%124,%125,%126,%127}, a, b, p, 1, 1, 0, 1;\n}\n"
    : "+f"(d[0]),"+f"(d[1]),"+f"(d[2]),"+f"(d[3]),"+f"(d[4]),"+f"(d[5]),"+f"(d[6]),"+f"(d[7]),"+f"(d[8]),"+f"(d[9]),"+f"(d[10]),"+f"(d[11]),"+f"(d[12]),"+f"(d[13]),"+f"(d[14]),"+f"(d[15]),"+f"(d[16]),"+f"(d[17]),"+f"(d[18]),"+f"(d[19]),"+f"(d[20]),"+f"(d[21]),"+f"(d[22]),"+f"(d[23]),"+f"(d[24]),"+f"(d[25]),"+f"(d[26]),"+f"(d[27]),"+f"(d[28]),"+f"(d[29]),"+f"(d[30]),"+f"(d[31]),"+f"(d[32]),"+f"(d[33]),"+f"(d[34]),"+f"(d[35]),"+f"(d[36]),"+f"(d[37]),"+f"(d[38]),"+f"(d[39]),"+f"(d[40]),"+f"(d[41]),"+f"(d[42]),"+f"(d[43]),"+f"(d[44]),"+f"(d[45]),"+f"(d[46]),"+f"(d[47]),"+f"(d[48]),"+f"(d[49]),"+f"(d[50]),"+f"(d[51]),"+f"(d[52]),"+f"(d[53]),"+f"(d[54]),"+f"(d[55]),"+f"(d[56]),"+f"(d[57]),"+f"(d[58]),"+f"(d[59]),"+f"(d[60]),"+f"(d[61]),"+f"(d[62]),"+f"(d[63]),"+f"(d[64]),"+f"(d[65]),"+f"(d[66]),"+f"(d[67]),"+f"(d[68]),"+f"(d[69]),"+f"(d[70]),"+f"(d[71]),"+f"(d[72]),"+f"(d[73]),"+f"(d[74]),"+f"(d[75]),"+f"(d[76]),"+f"(d[77]),"+f"(d[78]),"+f"(d[79]),"+f"(d[80]),"+f"(d[81]),"+f"(d[82]),"+f"(d[83]),"+f"(d[84]),"+f"(d[85]),"+f"(d[86]),"+f"(d[87]),"+f"(d[88]),"+f"(d[89]),"+f"(d[90]),"+f"(d[91]),"+f"(d[92]),"+f"(d[93]),"+f"(d[94]),"+f"(d[95]),"+f"(d[96]),"+f"(d[97]),"+f"(d[98]),"+f"(d[99]),"+f"(d[100]),"+f"(d[101]),"+f"(d[102]),"+f"(d[103]),"+f"(d[104]),"+f"(d[105]),"+f"(d[106]),"+f"(d[107]),"+f"(d[108]),"+f"(d[109]),"+f"(d[110]),"+f"(d[111]),"+f"(d[112]),"+f"(d[113]),"+f"(d[114]),"+f"(d[115]),"+f"(d[116]),"+f"(d[117]),"+f"(d[118]),"+f"(d[119]),"+f"(d[120]),"+f"(d[121]),"+f"(d[122]),"+f"(d[123]),"+f"(d[124]),"+f"(d[125]),"+f"(d[126]),"+f"(d[127])
    : "r"(da), "r"(db), "r"(sd), "n"((uint32_t)(CA >> 32)), "n"((uint32_t)(CB >> 32)));
}
template<uint64_t CA, uint64_t CB> __device__ __forceinline__ void wgmma_ss_128(float* d, uint32_t da, uint32_t db, int sd) {
  asm volatile("{\n.reg .pred p;\n.reg .b64 a, b;\nsetp.ne.b32 p, %66, 0;\nmov.b64 a, {%64, %67};\nmov.b64 b, {%65, %68};\n"
    "wgmma.mma_async.sync.aligned.m64n128k16.f32.bf16.bf16 {%0,%1,%2,%3,%4,%5,%6,%7,%8,%9,%10,%11,%12,%13,%14,%15,%16,%17,%18,%19,%20,%21,%22,%23,%24,%25,%26,%27,%28,%29,%30,%31,%32,%33,%34,%35,%36,%37,%38,%39,%40,%41,%42,%43,%44,%45,%46,%47,%48,%49,%50,%51,%52,%53,%54,%55,%56,%57,%58,%59,%60,%61,%62,%63}, a, b, p, 1, 1, 0, 1;\n}\n"
    : "+f"(d[0]),"+f"(d[1]),"+f"(d[2]),"+f"(d[3]),"+f"(d[4]),"+f"(d[5]),"+f"(d[6]),"+f"(d[7]),"+f"(d[8]),"+f"(d[9]),"+f"(d[10]),"+f"(d[11]),"+f"(d[12]),"+f"(d[13]),"+f"(d[14]),"+f"(d[15]),"+f"(d[16]),"+f"(d[17]),"+f"(d[18]),"+f"(d[19]),"+f"(d[20]),"+f"(d[21]),"+f"(d[22]),"+f"(d[23]),"+f"(d[24]),"+f"(d[25]),"+f"(d[26]),"+f"(d[27]),"+f"(d[28]),"+f"(d[29]),"+f"(d[30]),"+f"(d[31]),"+f"(d[32]),"+f"(d[33]),"+f"(d[34]),"+f"(d[35]),"+f"(d[36]),"+f"(d[37]),"+f"(d[38]),"+f"(d[39]),"+f"(d[40]),"+f"(d[41]),"+f"(d[42]),"+f"(d[43]),"+f"(d[44]),"+f"(d[45]),"+f"(d[46]),"+f"(d[47]),"+f"(d[48]),"+f"(d[49]),"+f"(d[50]),"+f"(d[51]),"+f"(d[52]),"+f"(d[53]),"+f"(d[54]),"+f"(d[55]),"+f"(d[56]),"+f"(d[57]),"+f"(d[58]),"+f"(d[59]),"+f"(d[60]),"+f"(d[61]),"+f"(d[62]),"+f"(d[63])
    : "r"(da), "r"(db), "r"(sd), "n"((uint32_t)(CA >> 32)), "n"((uint32_t)(CB >> 32)));
}
template<uint64_t CA, uint64_t CB> __device__ __forceinline__ void wgmma_ss_64(float* d, uint32_t da, uint32_t db, int sd) {
  asm volatile("{\n.reg .pred p;\n.reg .b64 a, b;\nsetp.ne.b32 p, %34, 0;\nmov.b64 a, {%32, %35};\nmov.b64 b, {%33, %36};\n"
    "wgmma.mma_async.sync.aligned.m64n64k16.f32.bf16.bf16 {%0,%1,%2,%3,%4,%5,%6,%7,%8,%9,%10,%11,%12,%13,%14,%15,%16,%17,%18,%19,%20,%21,%22,%23,%24,%25,%26,%27,%28,%29,%30,%31}, a, b, p, 1, 1, 0, 1;\n}\n"
    : "+f"(d[0]),"+f"(d[1]),"+f"(d[2]),"+f"(d[3]),"+f"(d[4]),"+f"(d[5]),"+f"(d[6]),"+f"(d[7]),"+f"(d[8]),"+f"(d[9]),"+f"(d[10]),"+f"(d[11]),"+f"(d[12]),"+f"(d[13]),"+f"(d[14]),"+f"(d[15]),"+f"(d[16]),"+f"(d[17]),"+f"(d[18]),"+f"(d[19]),"+f"(d[20]),"+f"(d[21]),"+f"(d[22]),"+f"(d[23]),"+f"(d[24]),"+f"(d[25]),"+f"(d[26]),"+f"(d[27]),"+f"(d[28]),"+f"(d[29]),"+f"(d[30]),"+f"(d[31])
    : "r"(da), "r"(db), "r"(sd), "n"((uint32_t)(CA >> 32)), "n"((uint32_t)(CB >> 32)));
}
template<uint64_t CA, uint64_t CB> __device__ __forceinline__ void wgmma_ss_112(float* d, uint32_t da, uint32_t db, int sd) {
  asm volatile("{\n.reg .pred p;\n.reg .b64 a, b;\nsetp.ne.b32 p, %58, 0;\nmov.b64 a, {%56, %59};\nmov.b64 b, {%57, %60};\n"
    "wgmma.mma_async.sync.aligned.m64n112k16.f32.bf16.bf16 {%0,%1,%2,%3,%4,%5,%6,%7,%8,%9,%10,%11,%12,%13,%14,%15,%16,%17,%18,%19,%20,%21,%22,%23,%24,%25,%26,%27,%28,%29,%30,%31,%32,%33,%34,%35,%36,%37,%38,%39,%40,%41,%42,%43,%44,%45,%46,%47,%48,%49,%50,%51,%52,%53,%54,%55}, a, b, p, 1, 1, 0, 1;\n}\n"
    : "+f"(d[0]),"+f"(d[1]),"+f"(d[2]),"+f"(d[3]),"+f"(d[4]),"+f"(d[5]),"+f"(d[6]),"+f"(d[7]),"+f"(d[8]),"+f"(d[9]),"+f"(d[10]),"+f"(d[11]),"+f"(d[12]),"+f"(d[13]),"+f"(d[14]),"+f"(d[15]),"+f"(d[16]),"+f"(d[17]),"+f"(d[18]),"+f"(d[19]),"+f"(d[20]),"+f"(d[21]),"+f"(d[22]),"+f"(d[23]),"+f"(d[24]),"+f"(d[25]),"+f"(d[26]),"+f"(d[27]),"+f"(d[28]),"+f"(d[29]),"+f"(d[30]),"+f"(d[31]),"+f"(d[32]),"+f"(d[33]),"+f"(d[34]),"+f"(d[35]),"+f"(d[36]),"+f"(d[37]),"+f"(d[38]),"+f"(d[39]),"+f"(d[40]),"+f"(d[41]),"+f"(d[42]),"+f"(d[43]),"+f"(d[44]),"+f"(d[45]),"+f"(d[46]),"+f"(d[47]),"+f"(d[48]),"+f"(d[49]),"+f"(d[50]),"+f"(d[51]),"+f"(d[52]),"+f"(d[53]),"+f"(d[54]),"+f"(d[55])
    : "r"(da), "r"(db), "r"(sd), "n"((uint32_t)(CA >> 32)), "n"((uint32_t)(CB >> 32)));
}
template<uint64_t CB> __device__ __forceinline__ void wgmma_rs_112(float* d, uint32_t a0, uint32_t a1, uint32_t a2, uint32_t a3, uint32_t db, int sd) {
  asm volatile("{\n.reg .pred p;\n.reg .b64 b;\nsetp.ne.b32 p, %61, 0;\nmov.b64 b, {%60, %62};\n"
    "wgmma.mma_async.sync.aligned.m64n112k16.f32.bf16.bf16 {%0,%1,%2,%3,%4,%5,%6,%7,%8,%9,%10,%11,%12,%13,%14,%15,%16,%17,%18,%19,%20,%21,%22,%23,%24,%25,%26,%27,%28,%29,%30,%31,%32,%33,%34,%35,%36,%37,%38,%39,%40,%41,%42,%43,%44,%45,%46,%47,%48,%49,%50,%51,%52,%53,%54,%55}, {%56,%57,%58,%59}, b, p, 1, 1, 1;\n}\n"
    : "+f"(d[0]),"+f"(d[1]),"+f"(d[2]),"+f"(d[3]),"+f"(d[4]),"+f"(d[5]),"+f"(d[6]),"+f"(d[7]),"+f"(d[8]),"+f"(d[9]),"+f"(d[10]),"+f"(d[11]),"+f"(d[12]),"+f"(d[13]),"+f"(d[14]),"+f"(d[15]),"+f"(d[16]),"+f"(d[17]),"+f"(d[18]),"+f"(d[19]),"+f"(d[20]),"+f"(d[21]),"+f"(d[22]),"+f"(d[23]),"+f"(d[24]),"+f"(d[25]),"+f"(d[26]),"+f"(d[27]),"+f"(d[28]),"+f"(d[29]),"+f"(d[30]),"+f"(d[31]),"+f"(d[32]),"+f"(d[33]),"+f"(d[34]),"+f"(d[35]),"+f"(d[36]),"+f"(d[37]),"+f"(d[38]),"+f"(d[39]),"+f"(d[40]),"+f"(d[41]),"+f"(d[42]),"+f"(d[43]),"+f"(d[44]),"+f"(d[45]),"+f"(d[46]),"+f"(d[47]),"+f"(d[48]),"+f"(d[49]),"+f"(d[50]),"+f"(d[51]),"+f"(d[52]),"+f"(d[53]),"+f"(d[54]),"+f"(d[55])
    : "r"(a0), "r"(a1), "r"(a2), "r"(a3), "r"(db), "r"(sd), "n"((uint32_t)(CB >> 32)));
}

constexpr int DM = 448;
constexpr int NCTA = 128;
#define MAPPING 1
#define GRID 132
#define PINGPONG 0
#define WIN 6
#define WIN_END 25
#define UNR_B 1
#define UNR_C 1
constexpr int kB = UNR_B, kC = UNR_C;
#define PACE 1
#define PACE_END 6
#define MAP_S 4
constexpr int SPIN_LIMIT = 1 << 22;

constexpr uint32_t OFF_X = 0, OFF_Y = 114688, OFF_MISC = 229376, SMEM_BYTES = 232448;
constexpr uint32_t Y_VR = 0, Y_K = 28672, Y_KOWN = 57344, Y_VOWN = 71680, Y_Q = 86016;
constexpr uint32_t HALF = 57344;
constexpr uint32_t M_BAR = OFF_MISC;
constexpr uint32_t M_ST = OFF_MISC + 512;
constexpr uint32_t M_G = OFF_MISC + 2304;
constexpr uint32_t M_EPOCH = OFF_MISC + 3040;
enum { B_XFULL = 0, B_FULLK = 7, B_FULLV = 8, B_FULLQ, B_KRFULL, B_VRFULL, B_WOFULL, B_XCH, B_FULL = 16, B_MOD1 = 28, B_MOD2, B_WMFULL,
       B_EMPTY = 32, B_XFREE = B_EMPTY + 12, B_GEMV, B_PEER,
       B_PUB = 47,
       B_WMFREE = 56, B_HRDY, B_GFULL = B_HRDY + 3, B_DONE = 31, B_DUMMY = B_GEMV };

__device__ uint32_t g_ticket;
__device__ __align__(128) uint32_t g_mod[8 * 6 * DM];
__device__ __align__(128) uint32_t g_flag[144 * 128];
constexpr int RB_WORDS = 262144, RB_KV = 0, RB_O = 57344, RB_X1 = 86016, RB_H2 = 143360, RB_ST = 258048;
__device__ __align__(128) uint32_t g_act[18 * RB_WORDS];
__device__ __align__(128) uint32_t g_wd[56 * 4 * 1792];
#define PROFH(id)
#define PROFH1(id)
#define PROFC(id)

struct alignas(64) Params {
    CUtensorMap wm, xm, qkv, wo, ga, ua, gb, ub, gc, uc, dn;
    const bf16 *x, *c, *wqkv, *wmod, *wg, *wu, *wd, *wop;
    bf16* out;
    uint32_t* actb;
    uint32_t zero;
};

__device__ __forceinline__ void mbar_init(uint32_t bar, int cnt) { asm volatile("mbarrier.init.shared::cta.b64 [%0], %1;" ::"r"(bar), "r"(cnt) : "memory"); }
__device__ __forceinline__ void mbar_expect_tx(uint32_t bar, uint32_t bytes) { asm volatile("mbarrier.arrive.expect_tx.shared::cta.b64 _, [%0], %1;" ::"r"(bar), "r"(bytes) : "memory"); }
__device__ __forceinline__ void mbar_arrive(uint32_t bar) { asm volatile("mbarrier.arrive.shared::cta.b64 _, [%0];" ::"r"(bar) : "memory"); }
__device__ __forceinline__ void mbar_wait(uint32_t bar, uint32_t parity) {
    uint32_t ok; int n = 0;
    do {
        asm volatile("{\n.reg .pred p;\nmbarrier.try_wait.parity.shared::cta.b64 p, [%1], %2;\nselp.u32 %0, 1, 0, p;\n}" : "=r"(ok) : "r"(bar), "r"(parity) : "memory");
        if (++n > SPIN_LIMIT) __trap();
    } while (!ok);
}
__device__ __forceinline__ void mbar_wait_c(uint32_t bar, uint32_t parity) {
    asm volatile("{\n.reg .pred p;\nWL:\nmbarrier.try_wait.parity.shared::cta.b64 p, [%0], %1;\n@!p bra WL;\n}" ::"r"(bar), "r"(parity) : "memory");
}
__device__ __forceinline__ void mbar_wait_cluster(uint32_t bar, uint32_t parity) {
    uint32_t ok; int n = 0;
    do {
        asm volatile("{\n.reg .pred p;\nmbarrier.try_wait.parity.acquire.cluster.shared::cta.b64 p, [%1], %2;\nselp.u32 %0, 1, 0, p;\n}" : "=r"(ok) : "r"(bar), "r"(parity) : "memory");
        if (++n > SPIN_LIMIT) __trap();
    } while (!ok);
}
__device__ __forceinline__ void warp_arrive(uint32_t bar) {
    __syncwarp();
    asm volatile("{\n.reg .pred p;\nelect.sync _|p, 0xffffffff;\n@p mbarrier.arrive.shared::cta.b64 _, [%0];\n}" ::"r"(bar) : "memory");
}
__device__ __forceinline__ int opaque(int v) { return __shfl_sync(~0u, v, 0); }
__device__ __forceinline__ int fresh_tid() { int v; asm volatile("mov.u32 %0, %%tid.x;" : "=r"(v)); return v; }
__device__ __forceinline__ void bar_sync(int id, int n) { asm volatile("bar.sync %0, %1;" ::"r"(id), "r"(n) : "memory"); }
__device__ __forceinline__ void bar_arrive(int id, int n) { asm volatile("bar.arrive %0, %1;" ::"r"(id), "r"(n) : "memory"); }
__device__ __forceinline__ void fence_async_smem() { asm volatile("fence.proxy.async.shared::cta;" ::: "memory"); }
__device__ __forceinline__ void fence_async_global() { asm volatile("fence.proxy.async.global;" ::: "memory"); }
__device__ __forceinline__ void fence_gpu() { asm volatile("fence.release.gpu;" ::: "memory"); }
__device__ __forceinline__ void tma3(uint32_t dst, const CUtensorMap* m, int c0, int c1, int c2, uint32_t bar) {
    asm volatile("cp.async.bulk.tensor.3d.shared::cluster.global.mbarrier::complete_tx::bytes [%0], [%1, {%3, %4, %5}], [%2];"
                 ::"r"(dst), "l"(m), "r"(bar), "r"(c0), "r"(c1), "r"(c2) : "memory");
}
__device__ __forceinline__ void bulk_load(uint32_t dst, const void* src, uint32_t bytes, uint32_t bar) {
    asm volatile("cp.async.bulk.shared::cluster.global.mbarrier::complete_tx::bytes [%0], [%1], %2, [%3];" ::"r"(dst), "l"(src), "r"(bytes), "r"(bar) : "memory");
}
__device__ __forceinline__ void expect_e(uint32_t bar, uint32_t bytes) {
    asm volatile("{\n.reg .pred p;\nelect.sync _|p, 0xffffffff;\n@p mbarrier.arrive.expect_tx.shared::cta.b64 _, [%0], %1;\n}" ::"r"(bar), "r"(bytes) : "memory");
}
__device__ __forceinline__ void tma3_e(uint32_t dst, const CUtensorMap* m, int c0, int c1, int c2, uint32_t bar) {
    asm volatile("{\n.reg .pred p;\nelect.sync _|p, 0xffffffff;\n@p cp.async.bulk.tensor.3d.shared::cluster.global.mbarrier::complete_tx::bytes [%0], [%1, {%3, %4, %5}], [%2];\n}"
                 ::"r"(dst), "l"(m), "r"(bar), "r"(c0), "r"(c1), "r"(c2) : "memory");
}
__device__ __forceinline__ void bulk_e(uint32_t dst, const void* src, uint32_t bytes, uint32_t bar) {
    asm volatile("{\n.reg .pred p;\nelect.sync _|p, 0xffffffff;\n@p cp.async.bulk.shared::cluster.global.mbarrier::complete_tx::bytes [%0], [%1], %2, [%3];\n}"
                 ::"r"(dst), "l"(src), "r"(bytes), "r"(bar) : "memory");
}
__device__ __forceinline__ void init_e(uint32_t bar, int cnt) {
    asm volatile("{\n.reg .pred p;\nelect.sync _|p, 0xffffffff;\n@p mbarrier.init.shared::cta.b64 [%0], %1;\n}" ::"r"(bar), "r"(cnt) : "memory");
}
__device__ __forceinline__ void l2_prefetch_e(const void* src, uint32_t bytes) {
    asm volatile("{\n.reg .pred p;\nelect.sync _|p, 0xffffffff;\n@p cp.async.bulk.prefetch.L2.global [%0], %1;\n}" ::"l"(src), "r"(bytes) : "memory");
}
__device__ __forceinline__ uint32_t ld_relaxed(const uint32_t* p) { uint32_t v; asm volatile("ld.relaxed.gpu.global.u32 %0, [%1];" : "=r"(v) : "l"(p) : "memory"); return v; }
__device__ __forceinline__ void st_relaxed(uint32_t* p, uint32_t v) { asm volatile("st.relaxed.gpu.global.u32 [%0], %1;" ::"l"(p), "r"(v) : "memory"); }
__device__ __forceinline__ uint4 ld_relaxed4(const uint4* p) { uint4 v; asm volatile("ld.relaxed.gpu.global.v4.u32 {%0,%1,%2,%3}, [%4];" : "=r"(v.x), "=r"(v.y), "=r"(v.z), "=r"(v.w) : "l"(p) : "memory"); return v; }
__device__ __forceinline__ void st_relaxed4(uint4* p, uint4 v) { asm volatile("st.relaxed.gpu.global.v4.u32 [%0], {%1,%2,%3,%4};" ::"l"(p), "r"(v.x), "r"(v.y), "r"(v.z), "r"(v.w) : "memory"); }
__device__ __forceinline__ uint4 ldg_nc4(const void* p) { uint4 v; asm volatile("ld.global.nc.L1::no_allocate.v4.u32 {%0,%1,%2,%3}, [%4];" : "=r"(v.x), "=r"(v.y), "=r"(v.z), "=r"(v.w) : "l"(p)); return v; }
__device__ __forceinline__ uint32_t ldg_nc(const void* p) { uint32_t v; asm volatile("ld.global.nc.u32 %0, [%1];" : "=r"(v) : "l"(p)); return v; }
__device__ __forceinline__ uint32_t ld_acquire(const uint32_t* p) { uint32_t v; asm volatile("ld.acquire.gpu.global.u32 %0, [%1];" : "=r"(v) : "l"(p) : "memory"); return v; }
__device__ __forceinline__ uint4 lds4(uint32_t a) { uint4 v; asm volatile("ld.shared.v4.u32 {%0,%1,%2,%3}, [%4];" : "=r"(v.x), "=r"(v.y), "=r"(v.z), "=r"(v.w) : "r"(a) : "memory"); return v; }
__device__ __forceinline__ float2 lds2f(uint32_t a) { float2 v; asm volatile("ld.shared.v2.f32 {%0,%1}, [%2];" : "=f"(v.x), "=f"(v.y) : "r"(a) : "memory"); return v; }
__device__ __forceinline__ uint32_t lds1(uint32_t a) { uint32_t v; asm volatile("ld.shared.u32 %0, [%1];" : "=r"(v) : "r"(a) : "memory"); return v; }
__device__ __forceinline__ void sts4(uint32_t a, uint4 v) { asm volatile("st.shared.v4.u32 [%0], {%1,%2,%3,%4};" ::"r"(a), "r"(v.x), "r"(v.y), "r"(v.z), "r"(v.w) : "memory"); }
__device__ __forceinline__ void sts2(uint32_t a, uint32_t x, uint32_t y) { asm volatile("st.shared.v2.u32 [%0], {%1,%2};" ::"r"(a), "r"(x), "r"(y) : "memory"); }
__device__ __forceinline__ void sts1(uint32_t a, uint32_t v) { asm volatile("st.shared.u32 [%0], %1;" ::"r"(a), "r"(v) : "memory"); }
__device__ __forceinline__ void stsm4(uint32_t a, uint32_t r0, uint32_t r1, uint32_t r2, uint32_t r3) {
    asm volatile("stmatrix.sync.aligned.m8n8.x4.shared.b16 [%0], {%1,%2,%3,%4};" ::"r"(a), "r"(r0), "r"(r1), "r"(r2), "r"(r3));
}
__device__ __forceinline__ uint32_t pack2(float lo, float hi) { uint32_t r; asm("cvt.rn.bf16x2.f32 %0, %1, %2;" : "=r"(r) : "f"(hi), "f"(lo)); return r; }
__device__ __forceinline__ uint32_t pack2_relu(float lo, float hi) { uint32_t r; asm("cvt.rn.relu.bf16x2.f32 %0, %1, %2;" : "=r"(r) : "f"(hi), "f"(lo)); return r; }
__device__ __forceinline__ uint32_t hfma2(uint32_t a, uint32_t b, uint32_t c) { uint32_t r; asm("fma.rn.bf16x2 %0, %1, %2, %3;" : "=r"(r) : "r"(a), "r"(b), "r"(c)); return r; }
__device__ __forceinline__ uint32_t hmul2(uint32_t a, uint32_t b) { uint32_t r; asm("mul.rn.bf16x2 %0, %1, %2;" : "=r"(r) : "r"(a), "r"(b)); return r; }
__device__ __forceinline__ float bf_lo(uint32_t v) { return __uint_as_float(v << 16); }
__device__ __forceinline__ float bf_hi(uint32_t v) { return __uint_as_float(v & 0xFFFF0000u); }
__device__ __forceinline__ float bf_round(float v) { return bf_lo(pack2(v, 0.f)); }
__device__ __forceinline__ float ex2(float x) { float r; asm("ex2.approx.ftz.f32 %0, %1;" : "=f"(r) : "f"(x)); return r; }
__device__ __forceinline__ void mma16816(float* d, uint32_t a0, uint32_t a1, uint32_t a2, uint32_t a3, uint32_t b0, uint32_t b1) {
    asm("mma.sync.aligned.m16n8k16.row.col.f32.bf16.bf16.f32 {%0,%1,%2,%3}, {%4,%5,%6,%7}, {%8,%9}, {%0,%1,%2,%3};"
        : "+f"(d[0]), "+f"(d[1]), "+f"(d[2]), "+f"(d[3]) : "r"(a0), "r"(a1), "r"(a2), "r"(a3), "r"(b0), "r"(b1));
}
__device__ __forceinline__ void mma16816_first(float* d, uint32_t a0, uint32_t a1, uint32_t a2, uint32_t a3, uint32_t b0, uint32_t b1) {
    asm volatile("mma.sync.aligned.m16n8k16.row.col.f32.bf16.bf16.f32 {%0,%1,%2,%3}, {%4,%5,%6,%7}, {%8,%9}, {%10,%10,%10,%10};"
        : "=f"(d[0]), "=f"(d[1]), "=f"(d[2]), "=f"(d[3]) : "r"(a0), "r"(a1), "r"(a2), "r"(a3), "r"(b0), "r"(b1), "f"(0.f));
}
__device__ __forceinline__ void mma16816_v(float* d, uint32_t a0, uint32_t a1, uint32_t a2, uint32_t a3, uint32_t b0, uint32_t b1) {
    asm volatile("mma.sync.aligned.m16n8k16.row.col.f32.bf16.bf16.f32 {%0,%1,%2,%3}, {%4,%5,%6,%7}, {%8,%9}, {%0,%1,%2,%3};"
        : "+f"(d[0]), "+f"(d[1]), "+f"(d[2]), "+f"(d[3]) : "r"(a0), "r"(a1), "r"(a2), "r"(a3), "r"(b0), "r"(b1));
}
__device__ __forceinline__ void mma1688(float* d, uint32_t a0, uint32_t a1, uint32_t b0) {
    asm("mma.sync.aligned.m16n8k8.row.col.f32.bf16.bf16.f32 {%0,%1,%2,%3}, {%4,%5}, {%6}, {%0,%1,%2,%3};"
        : "+f"(d[0]), "+f"(d[1]), "+f"(d[2]), "+f"(d[3]) : "r"(a0), "r"(a1), "r"(b0));
}
__device__ __forceinline__ void ldsm4(uint32_t a, uint32_t* r) {
    asm volatile("ldmatrix.sync.aligned.m8n8.x4.shared.b16 {%0,%1,%2,%3}, [%4];" : "=r"(r[0]), "=r"(r[1]), "=r"(r[2]), "=r"(r[3]) : "r"(a));
}
__device__ __forceinline__ void ldsm4t(uint32_t a, uint32_t* r) {
    asm volatile("ldmatrix.sync.aligned.m8n8.x4.trans.shared.b16 {%0,%1,%2,%3}, [%4];" : "=r"(r[0]), "=r"(r[1]), "=r"(r[2]), "=r"(r[3]) : "r"(a));
}
__device__ __forceinline__ float rcp(float x) { float r; asm("rcp.approx.ftz.f32 %0, %1;" : "=f"(r) : "f"(x)); return r; }
__device__ __forceinline__ uint2 ld_relaxed2(const void* p) { uint2 v; asm volatile("ld.relaxed.gpu.global.v2.u32 {%0,%1}, [%2];" : "=r"(v.x), "=r"(v.y) : "l"(p) : "memory"); return v; }
__device__ __forceinline__ void st_relaxed2(void* p, uint32_t x, uint32_t y) { asm volatile("st.relaxed.gpu.global.v2.u32 [%0], {%1,%2};" ::"l"(p), "r"(max(x, 1u)), "r"(max(y, 1u)) : "memory"); }
__host__ __device__ constexpr uint64_t dconst(uint32_t lbo, uint32_t sbo, uint32_t swz) {
    return ((uint64_t)(lbo >> 4) << 16) | ((uint64_t)(sbo >> 4) << 32) | ((uint64_t)swz << 62);
}
__device__ __forceinline__ uint32_t mkdesc(uint32_t addr, uint64_t c) { return (uint32_t)c | ((addr & 0x3FFFF) >> 4); }
#define WG_FENCE() asm volatile("wgmma.fence.sync.aligned;" ::: "memory")
#define WG_COMMIT() asm volatile("wgmma.commit_group.sync.aligned;" ::: "memory")
#define WG_WAIT(n) asm volatile("wgmma.wait_group.sync.aligned %0;" ::"n"(n) : "memory")
template <int N> __device__ __forceinline__ void reg_fence(float* d) {
#pragma unroll
    for (int i = 0; i < N; i++) asm volatile("" : "+f"(d[i])::"memory");
}
template <int N> __device__ __forceinline__ void reg_def(float* d) {
#pragma unroll
    for (int i = 0; i < N; i++) asm volatile("" : "=f"(d[i]));
}
template <int N> __device__ __forceinline__ void reg_def(uint32_t* d) {
#pragma unroll
    for (int i = 0; i < N; i++) asm volatile("" : "=r"(d[i]));
}
__device__ __forceinline__ bool is_unset(uint4 v) { return min(min(v.x, v.y), min(v.z, v.w)) == 0u; }
__device__ __forceinline__ uint4 nz4(uint32_t a, uint32_t b, uint32_t c, uint32_t d) { return make_uint4(max(a, 1u), max(b, 1u), max(c, 1u), max(d, 1u)); }
__device__ __forceinline__ void wait_flags(const uint32_t* p, uint32_t target, uint32_t mask) {
    int n = 0;
    while (~__ballot_sync(~0u, (int)(ld_relaxed(p) - target) >= 0) & mask) { if (++n > SPIN_LIMIT) __trap(); }
    asm volatile("fence.acquire.gpu;" ::: "memory");
}
__device__ __forceinline__ float silu_bf(uint32_t cbits) {
    const float c = __uint_as_float(cbits << 16);
    return bf_round(__fdividef(c, 1.f + fminf(ex2(-1.4426950408889634f * c), 1e30f)));
}
__device__ __forceinline__ void gemv_part(uint32_t wmbuf, int npanel, int wp, int lane) {
    const uint32_t wa = wmbuf + wp * 512 + (8 * (lane >> 4) + (lane & 7)) * 32 + ((lane >> 3) & 1) * 16;
    uint2 B[4];
#pragma unroll
    for (int i = 0; i < 4; i++) { const float2 v = lds2f(wmbuf + 28672 + (wp + 8 * i) * 32 + (lane & 3) * 8); B[i] = make_uint2(__float_as_uint(v.x), __float_as_uint(v.y)); }
#pragma unroll 1
    for (int pn = 0; pn < npanel; pn++) {
        float d[4] = {};
        uint32_t A[16];
#pragma unroll
        for (int i = 0; i < 4; i++) ldsm4t(wa + pn * 14336 + (i < 3 || wp < 4 ? i : 0) * 4096, A + 4 * i);
#pragma unroll
        for (int i = 0; i < 4; i++) mma16816(d, A[4 * i], A[4 * i + 1], A[4 * i + 2], A[4 * i + 3], B[i].x, B[i].y);
        if ((lane & 3) == 0) {
            sts1(wmbuf + 29696 + (wp * 32 + pn * 16 + (lane >> 2)) * 4, __float_as_uint(d[0]));
            sts1(wmbuf + 29696 + (wp * 32 + pn * 16 + 8 + (lane >> 2)) * 4, __float_as_uint(d[2]));
        }
    }
}
__device__ __forceinline__ int pass_f(int fs, int ps) { return 224 * fs + ((fs & 1) ? (ps == 0 ? 96 : ps == 1 ? 32 : 0) : (ps == 0 ? 0 : ps == 1 ? 128 : 192)); }
__device__ __forceinline__ constexpr uint32_t slot_off(int l) { return l * 16384; }
__device__ __forceinline__ void x1_fix(uint32_t* x, const uint32_t* g) {
    uint32_t mn;
    do {
        mn = ~0u;
#pragma unroll
        for (int i = 0; i < 16; i++) { x[i] = ld_relaxed(g + (i >> 1) * 256 + (i & 1) * 32); mn = min(mn, x[i]); }
    } while (__any_sync(~0u, mn == 0u));
}
__device__ __forceinline__ void ln_coeffs(float mean, float msq, uint32_t& r2, uint32_t& n2) {
    const float rs = bf_round(rsqrtf(fmaxf(msq - mean * mean, 0.f) + 1e-5f));
    r2 = pack2(rs, rs);
    n2 = pack2(-mean * rs, -mean * rs);
}

#define LOADW bulk_e(dst, g_wd + (size_t)((f >> 5) * 4 + nq) * 1792, 7168, bar);
template <int sec> __device__ __forceinline__ void ring_loader(const Params& p, uint32_t sb_, int r_, int j_, int lane) {
    const uint32_t sb = opaque(sb_);
    const int r = opaque(r_), j = opaque(j_), nq = j >> 1, fs = 4 * (j & 1) + nq;
    const int fa = pass_f(fs, 0), fb = pass_f(fs, 1), fc = pass_f(fs, 2);
#define BAR(i) (sb + M_BAR + 8 * (i))
#define kh (j & 1)
            int sl = 0;
            mbar_wait(BAR(B_PUB + 2), 0);
            wait_flags(g_flag + (8 * r + j) * 128 + 96 + lane, lds1(sb + M_EPOCH) + 1, 0xFFFFu);
            fence_async_global();
#pragma unroll 1
            for (int s = 0; s < 28; s++) {
                if (s >= PACE && s < PACE_END) mbar_wait(BAR(B_FULL + s - PACE), 0);
                const int ps = s < 14 ? 0 : s < 21 ? 1 : 2;
                const uint32_t half = ps < 2 ? 8192 : 4096;
                mbar_wait(BAR(B_EMPTY + sl), (s >= 7 && s < 14) || s >= 21);
                expect_e(BAR(B_FULL + sl), half);
                tma3_e(sb + slot_off(sl) + sec * half, &p.ga + 2 * ps + sec, 0, ps ? 64 * sl : 32 * s, ps == 0 ? fa >> 6 : ps == 1 ? fb >> 6 : fc >> 5, BAR(B_FULL + sl));
                sl = sl == 6 ? 0 : sl + 1;
            }
            if (!sec) PROFH(3);
#pragma unroll 1
            for (int e = 0; e < 4; e++) {
                const uint32_t dst = sb + slot_off(e) + sec * 8192, bar = BAR(B_FULL + e);
                const int f = (e < 2 ? fa + 64 * e : e == 2 ? fb : fc) + 32 * sec;
                mbar_wait(BAR(B_EMPTY + e), 0);
                expect_e(bar, e == 3 && sec ? 0 : 7168);
                if (!(e == 3 && sec)) { LOADW }
            }
            sl = 4;
            int e = 4;
#pragma unroll 1
            for (int grp = 0; grp < 9; grp++) {
                const int ps = grp >= 6 ? 2 : grp >= 3 ? 1 : 0;
                int sidx = grp - 3 * ps;
                if (sec && sidx == 0) { mbar_wait(BAR(B_HRDY + ps), 0); fence_async_global(); }
                sidx += sidx >= nq;
                int f = pass_f(4 * kh + sidx, ps);
#pragma unroll 1
                for (int k = 4 >> ps; k > 0; k--, e++, f += 32) {
                    const uint32_t dst = sb + slot_off(sl), bar = BAR(B_FULL + sl);
                    mbar_wait(BAR(B_EMPTY + sl), e >= 12 && e < 24);
                    if (e < WIN_END && e >= WIN) mbar_wait(BAR(B_FULL + (sl >= WIN ? sl - WIN : sl + 12 - WIN)), e - WIN >= 12);
                    expect_e(bar, sec ? 8192 : 7168);
                    if (!sec) { LOADW }
                    else bulk_e(dst + 8192, p.actb + (size_t)r * RB_WORDS + RB_H2 + f * 64, 8192, bar);
                    sl = sl == 11 ? 0 : sl + 1;
                }
            }
            if (!sec) PROFH(4);
}

__global__ void __cluster_dims__(2, 1, 1) __launch_bounds__(384, 1) fused_block_kernel(const __grid_constant__ Params p) {
    extern __shared__ __align__(1024) unsigned char smem[];
    const uint32_t sb = (uint32_t)__cvta_generic_to_shared(smem);
    const int tid = threadIdx.x, lane = tid & 31, warp = __shfl_sync(~0u, tid >> 5, 0);
    const int m = blockIdx.x >> 1;
    int r, nq;
    {
        int g, i;
        if (m < MAP_S) { g = m < 4 ? 15 : 16; i = m & 3; }
        else if (m < MAP_S + 32) { g = (m - MAP_S) & 7; i = (m - MAP_S) >> 3; }
        else if (m < MAP_S + 60) { i = (m - MAP_S - 32) / 7; g = 8 + (m - MAP_S - 32) - 7 * i; }
        else { g = 16; i = m & 3; }
        r = g; nq = i;
    }
    const int j = opaque(2 * nq + (blockIdx.x & 1)), b = 8 * r + j, fs = 4 * kh + nq;
#define act (p.actb + (size_t)r * RB_WORDS)
    const uint32_t sc = r == 16;
    if (lane == 0 && warp < 9 && warp != 6 && warp != 7) {
        const int i0 = warp == 8 ? 0 : 8 + 8 * warp, cnt = warp == 0 || warp == 8 ? 1 : warp < 3 ? 2 : 8;
#pragma unroll
        for (int k = 0; k < 8; k++) if (i0 + k != B_WMFULL) mbar_init(BAR(i0 + k), cnt);
        asm volatile("fence.mbarrier_init.release.cluster;" ::: "memory");
        fence_async_smem();
    }

    if (warp < 8) {
        const int w = warp >> 2, wi = warp & 3;
#define COORDS const int t = fresh_tid() & 127, lane = t & 31, q = lane & 3, lr = lane >> 2, ra = 64 * w + 16 * wi + lr; \
        const uint32_t lx = (lane >> 4) ^ (lane & 7), mrow = (64 * w + 16 * wi + ((lane >> 3) & 1) * 8 + (lane & 7)) * 128; \
        (void)q; (void)lr; (void)ra; (void)lx; (void)mrow;
        const int sid = 2 * (j & 3) + w;
#define RUN(k) (!sc || sid == (k))
#define WAIT(i, par) mbar_wait_c(BAR(i), (par) | sc)
        constexpr uint64_t DB128 = dconst(4096, 1024, 1);
        bar_arrive(9, 384);
        bar_sync(0, 384);
        asm volatile("barrier.cluster.arrive.relaxed.aligned;" ::: "memory");
        asm volatile("setmaxnreg.inc.sync.aligned.u32 224;");
        PROFC(0);
        uint32_t xr[16];
        {
            COORDS
            uint32_t h[112];
            if (RUN(0)) {
                float ds[4] = {}, da[2][4] = {}, db[2][4] = {};
                const uint32_t ONE2 = 0x3F803F80u;
                if (kh == 0) { WAIT(B_WMFULL, 0); gemv_part(sb + OFF_Y + HALF, 1, warp, lane); warp_arrive(BAR(B_GEMV)); }
#pragma unroll
                for (int kb = 0; kb < 7; kb++) {
                    WAIT(B_XFULL + kb, 0);
#pragma unroll
                    for (int k4 = 0; k4 < 4; k4++) ldsm4(sb + OFF_X + mrow + kb * 16384 + (((2 * k4) ^ lx) << 4), h + 16 * kb + 4 * k4);
#pragma unroll
                    for (int k4 = 0; k4 < 4; k4++) {
                        const uint32_t* f = h + 16 * kb + 4 * k4;
                        mma16816(ds, f[0], f[1], f[2], f[3], ONE2, ONE2);
                        mma1688(da[0], f[0], f[1], f[0]); mma1688(db[0], f[0], f[1], f[1]);
                        mma1688(da[1], f[2], f[3], f[2]); mma1688(db[1], f[2], f[3], f[3]);
                    }
                }
#pragma unroll
                for (int i = 0; i < 4; i++) {
                    const int ch = 7 * j + 2 * i + (lane >> 4);
                    ldsm4(sb + OFF_X + mrow + (ch >> 3) * 16384 + (((ch ^ lane) & 7) << 4), xr + 4 * i);
                }
                warp_arrive(BAR(B_XFREE));
                float qa = (lr & 1) ? da[0][1] + da[1][1] : da[0][0] + da[1][0];
                float qb = (lr & 1) ? db[0][3] + db[1][3] : db[0][2] + db[1][2];
                const int src = (lane & ~3) | (lr >> 1);
                qa = __shfl_sync(~0u, qa, src);
                qb = __shfl_sync(~0u, qb, src);
                uint32_t ra2, na2, rb2, nb2;
                ln_coeffs(ds[0] * (1.f / DM), qa * (1.f / DM), ra2, na2);
                ln_coeffs(ds[2] * (1.f / DM), qb * (1.f / DM), rb2, nb2);
#pragma unroll
                for (int i = 0; i < 112; i += 2) { h[i] = hfma2(h[i], ra2, na2); h[i + 1] = hfma2(h[i + 1], rb2, nb2); }
                if (kh == 1) { WAIT(B_WMFULL, 0); gemv_part(sb + OFF_Y + HALF, 2, warp, lane); warp_arrive(BAR(B_GEMV)); }
            } else { reg_def<112>(h); reg_def<16>(xr); }
            PROFC(1);
            if (RUN(1)) {
                float ak[28], av[28], aq[28];
                uint32_t kp[14], vp[14];
                const uint32_t bk0 = mkdesc(sb + OFF_Y, DB128) + kh, bv0 = mkdesc(sb + OFF_Y + HALF, DB128) + kh, bq0 = mkdesc(sb + OFF_X, DB128) + kh;
                uint32_t* kvg = act + RB_KV + j * 7168 + (8 * w + 2 * wi) * 224 + lane;
                WAIT(B_FULLK, 0);
                WAIT(B_MOD1, 0);
                PROFC(2);
                reg_def<28>(ak);
#pragma unroll
                for (int g4 = 0; g4 < 4; g4++) {
#pragma unroll
                    for (int ks = 7 * g4; ks < 7 * g4 + 7; ks++) {
                        const uint4 st = *(const uint4*)(smem + M_ST + ks * 64 + q * 16);
                        h[4 * ks] = hfma2(h[4 * ks], st.x, st.y); h[4 * ks + 1] = hfma2(h[4 * ks + 1], st.x, st.y);
                        h[4 * ks + 2] = hfma2(h[4 * ks + 2], st.z, st.w); h[4 * ks + 3] = hfma2(h[4 * ks + 3], st.z, st.w);
                    }
                    WG_FENCE();
#pragma unroll
                    for (int ks = 7 * g4; ks < 7 * g4 + 7; ks++) wgmma_rs_56<DB128>(ak, h[4 * ks], h[4 * ks + 1], h[4 * ks + 2], h[4 * ks + 3], bk0 + ks * 128, ks != 0);
                }
                WG_COMMIT();
                PROFC(3);
                WAIT(B_FULLV, 0);
                reg_def<28>(av);
                WG_FENCE();
#pragma unroll
                for (int ks = 0; ks < 8; ks++) wgmma_rs_56<DB128>(av, h[4 * ks], h[4 * ks + 1], h[4 * ks + 2], h[4 * ks + 3], bv0 + ks * 128, ks != 0);
                WG_COMMIT();
                WG_WAIT(1);
                reg_fence<28>(ak);
#pragma unroll
                for (int g = 0; g < 7; g++) {
                    kp[2 * g] = pack2(ak[4 * g], ak[4 * g + 1]); kp[2 * g + 1] = pack2(ak[4 * g + 2], ak[4 * g + 3]);
                    kvg[g * 32] = kp[2 * g]; kvg[224 + g * 32] = kp[2 * g + 1];
                }
                warp_arrive(BAR(B_PUB));
                PROFC(4);
                WG_FENCE();
#pragma unroll
                for (int ks = 8; ks < 28; ks++) wgmma_rs_56<DB128>(av, h[4 * ks], h[4 * ks + 1], h[4 * ks + 2], h[4 * ks + 3], bv0 + ks * 128, 1);
                WG_COMMIT();
                WAIT(B_FULLQ, 0);
                reg_def<28>(aq);
                WG_FENCE();
#pragma unroll
                for (int ks = 0; ks < 8; ks++) wgmma_rs_56<DB128>(aq, h[4 * ks], h[4 * ks + 1], h[4 * ks + 2], h[4 * ks + 3], bq0 + ks * 128, ks != 0);
                WG_COMMIT();
                WG_WAIT(1);
                reg_fence<28>(av);
#pragma unroll
                for (int g = 0; g < 7; g++) {
                    vp[2 * g] = pack2(av[4 * g], av[4 * g + 1]); vp[2 * g + 1] = pack2(av[4 * g + 2], av[4 * g + 3]);
                    kvg[3584 + g * 32] = vp[2 * g]; kvg[3584 + 224 + g * 32] = vp[2 * g + 1];
                }
                warp_arrive(BAR(B_PUB + 1));
                PROFC(5);
                WG_FENCE();
#pragma unroll
                for (int ks = 8; ks < 28; ks++) wgmma_rs_56<DB128>(aq, h[4 * ks], h[4 * ks + 1], h[4 * ks + 2], h[4 * ks + 3], bq0 + ks * 128, 1);
                WG_COMMIT();
                WAIT(B_PUB + 1, 0);
                const uint32_t ko = sb + OFF_Y + Y_KOWN + (8 * w + 2 * wi) * 896 + lane * 4;
                const uint32_t qo = sb + OFF_Y + Y_Q + (8 * w + 2 * wi) * 1024 + lane * 4;
#pragma unroll
                for (int g = 0; g < 7; g++) {
                    sts1(ko + g * 128, kp[2 * g]); sts1(ko + 896 + g * 128, kp[2 * g + 1]);
                    sts1(ko + (Y_VOWN - Y_KOWN) + g * 128, vp[2 * g]); sts1(ko + (Y_VOWN - Y_KOWN) + 896 + g * 128, vp[2 * g + 1]);
                }
                WG_WAIT(0);
                reg_fence<28>(aq);
                __syncwarp();
                if (lane < 3 && w == 1) mbar_arrive(BAR(B_EMPTY + lane));
#pragma unroll
                for (int g = 0; g < 7; g++) {
                    const uint32_t q0 = pack2(aq[4 * g], aq[4 * g + 1]), q1 = pack2(aq[4 * g + 2], aq[4 * g + 3]);
                    if (g == 3) {
                        sts1(qo + 3 * 128, q < 2 ? q0 : 0u); sts1(qo + 1024 + 3 * 128, q < 2 ? q1 : 0u);
                        sts1(qo + 4 * 128, q < 2 ? 0u : q0); sts1(qo + 1024 + 4 * 128, q < 2 ? 0u : q1);
                    } else {
                        const int ch = g < 3 ? g : g + 1;
                        sts1(qo + ch * 128, q0); sts1(qo + 1024 + ch * 128, q1);
                    }
                }
                if (!sc) bar_sync(3, 256);
            }
        }
        PROFC(6);
        WAIT(B_KRFULL, 0);
        PROFC(7);
        if (RUN(2)) {
#pragma unroll 1
            for (int hf = sc; hf < 2; hf++) {
                COORDS
                float s[136];
                float na = 0.f, nb = 0.f;
                const float CS = 0.18898223650461361f * 1.4426950408889634f;
                const int kg0 = 8 * hf + 2 * wi;
                const int pmin = 16 - 8 * r - 4 * hf - wi;
                const float NEG = __int_as_float(0xFF800000);
                {
                    uint32_t F[8];
                    const uint32_t qa = sb + OFF_Y + Y_Q + (kg0 + ((lane >> 3) & 1)) * 1024 + (4 * w + (lane >> 4)) * 128 + (lane & 7) * 16;
                    ldsm4(qa, F); ldsm4(qa + 256, F + 4);
                    uint32_t ka = sb + OFF_Y + Y_K + kg0 * 896 + (3 * w + (lane >> 3)) * 128 + (lane & 7) * 16;
#pragma unroll
                    for (int g = 0; g < 34; g++) {
                        uint32_t B[4];
                        if (g >= 12 && g % 4 == 0) ka += __float_as_uint(s[4 * (g - 12)]) & p.zero;
                        ldsm4(ka + g * 896, B);
                        mma16816_first(s + 4 * g, F[0], F[1], F[2], F[3], B[0], B[1]);
                        mma16816_v(s + 4 * g, F[4], F[5], F[6], F[7], B[2], B[3]);
                    }
                    const bool c0 = 2 * q > lr, c1 = 2 * q + 1 > lr;
                    if (!c0) { s[0] = NEG; s[6] = NEG; }
                    if (!c1) { s[1] = NEG; s[7] = NEG; }
                    s[2] = NEG; s[3] = NEG;
                    if (c0) { s[128] = NEG; s[134] = NEG; }
                    if (c1) { s[129] = NEG; s[135] = NEG; }
                    s[132] = NEG; s[133] = NEG;
                    float ma = NEG, mb = NEG;
#pragma unroll
                    for (int pp = 0; pp < 17; pp++) {
                        const float* e = s + 8 * pp;
                        const float bias = pp < pmin ? NEG : 0.f;
                        ma = fmaxf(ma, fmaxf(fmaxf(e[0], e[1]), fmaxf(e[4], e[5])) + bias);
                        mb = fmaxf(mb, fmaxf(fmaxf(e[2], e[3]), fmaxf(e[6], e[7])) + bias);
                    }
                    ma = fmaxf(ma, __shfl_xor_sync(~0u, ma, 1)); mb = fmaxf(mb, __shfl_xor_sync(~0u, mb, 1));
                    ma = fmaxf(ma, __shfl_xor_sync(~0u, ma, 2)); mb = fmaxf(mb, __shfl_xor_sync(~0u, mb, 2));
                    na = -ma * CS; nb = -mb * CS;
                }
                PROFC(8 + 3 * hf);
                {
                    WAIT(B_VRFULL, 0);
                    float o[16] = {}, rs[4] = {};
                    uint32_t pk[2];
                    const uint32_t va = sb + OFF_Y + Y_VR + (kg0 + ((lane >> 3) & 1)) * 896 + (3 * w + (lane >> 4)) * 128 + (lane & 7) * 16;
#pragma unroll
                    for (int pp = 0; pp < 17; pp++) {
                        uint32_t B[8];
                        const uint32_t v = va + pp * 1792 + (pp == 16 || (pp >= 9 && kg0 + 2 * pp >= 32) ? Y_VOWN - 32 * 896 : 0);
                        ldsm4t(v, B); ldsm4t(v + 256, B + 4);
                        float e[8];
                        const float bias = __uint_as_float((pp < pmin ? 0xFF800000u : 0u) | ((pp < 2 ? B[0] : pk[pp & 1]) & p.zero));
#pragma unroll
                        for (int i = 0; i < 8; i++) e[i] = ex2(fmaf(s[8 * pp + i], CS, ((i & 2) ? nb : na) + bias));
                        const uint32_t p0 = pack2(e[0], e[1]), p1 = pack2(e[2], e[3]), p2 = pack2(e[4], e[5]), p3 = pack2(e[6], e[7]);
                        pk[pp & 1] = p3;
                        mma16816(rs, p0, p1, p2, p3, 0x3F803F80u, 0x3F803F80u);
#pragma unroll
                        for (int g = 0; g < 4; g++) mma16816(o + 4 * g, p0, p1, p2, p3, B[2 * g], B[2 * g + 1]);
                    }
                    PROFC(9 + 3 * hf);
                    const float ia = rcp(rs[0]), ib = rcp(rs[2]);
                    uint32_t* og = act + RB_O + hf * 14336 + (7 * j + 3 * w) * 256 + wi * 64 + lane;
#pragma unroll
                    for (int g = 0; g < 4; g++) {
                        if ((g == 3 - 3 * w) ? ((q >> 1) == w) : true) {
                            og[g * 256] = pack2(o[4 * g] * ia, o[4 * g + 1] * ia);
                            og[g * 256 + 32] = pack2(o[4 * g + 2] * ib, o[4 * g + 3] * ib);
                        }
                    }
                    warp_arrive(BAR(B_PUB + 2 + hf));
                    PROFC(10 + 3 * hf);
                }
            }
        }
        uint32_t x1p[14];
        COORDS
        constexpr uint64_t DT = dconst(1024, 128, 0);
        const int tile = opaque((lds1(sb + M_EPOCH) & 1) * 2 + w);
        if (RUN(4)) {
            float ac[28];
            const uint32_t ad = mkdesc(sb + (w ? OFF_Y + HALF : OFF_X), DT), bd = mkdesc(sb + OFF_X + HALF, DB128) + kh;
            WAIT(B_WOFULL, 0);
            WAIT(B_MOD2, 0);
            WAIT(B_GFULL + w, 0);
            PROFC(28);
            reg_def<28>(ac);
#pragma unroll 1
            for (int u = 0; u < 4; u++) {
                if (u == 2) WAIT(B_XFULL + 2 + w, 1);
                WG_FENCE();
#pragma unroll
                for (int i = 0; i < 7; i++) wgmma_ss_56<DT, DB128>(ac, ad + (7 * u + i) * 128, bd + (7 * u + i) * 128, (u | i) != 0);
            }
            WG_COMMIT();
            WG_WAIT(0);
            reg_fence<28>(ac);
            PROFC(14);
            __syncwarp();
            if (lane < 4) mbar_arrive(BAR(B_EMPTY + 3 + lane));
            if (lane < 3 && w == 0) mbar_arrive(BAR(B_EMPTY + lane));
            float s1a = 0.f, s2a = 0.f, s1b = 0.f, s2b = 0.f;
            uint32_t* xo = act + RB_X1 + tile * 14336 + 7 * j * 256 + wi * 64 + lane;
#pragma unroll
            for (int g = 0; g < 7; g++) {
                const float2 ga = *(const float2*)(smem + M_G + (8 * g + 2 * q) * 4);
                x1p[2 * g] = pack2(fmaf(ga.x, ac[4 * g], bf_lo(xr[2 * g])), fmaf(ga.y, ac[4 * g + 1], bf_hi(xr[2 * g])));
                x1p[2 * g + 1] = pack2(fmaf(ga.x, ac[4 * g + 2], bf_lo(xr[2 * g + 1])), fmaf(ga.y, ac[4 * g + 3], bf_hi(xr[2 * g + 1])));
                st_relaxed(xo + g * 256, max(x1p[2 * g], 1u)); st_relaxed(xo + g * 256 + 32, max(x1p[2 * g + 1], 1u));
                const float u0 = bf_lo(x1p[2 * g]), u1 = bf_hi(x1p[2 * g]), u2 = bf_lo(x1p[2 * g + 1]), u3 = bf_hi(x1p[2 * g + 1]);
                s1a += u0 + u1; s2a += u0 * u0 + u1 * u1; s1b += u2 + u3; s2b += u2 * u2 + u3 * u3;
            }
            float ka = (q & 1) ? s2a : s1a, kb2 = (q & 1) ? s2b : s1b;
            ka += __shfl_xor_sync(~0u, (q & 1) ? s1a : s2a, 1); kb2 += __shfl_xor_sync(~0u, (q & 1) ? s1b : s2b, 1);
            const float kk = ((q & 2) ? kb2 : ka) + __shfl_xor_sync(~0u, (q & 2) ? ka : kb2, 2);
            st_relaxed(act + RB_ST + ((tile * 8 + j) * 64 + 16 * wi + lr + 4 * (q & 2)) * 2 + (q & 1), max(__float_as_uint(kk), 1u));
            __syncwarp();
            if (lane < 2) mbar_arrive(BAR(B_PUB + 4 + w));
        } else reg_def<14>(x1p);
        PROFC(15);
        uint32_t h2a[32], h2b[24];
        {
            const int fa = pass_f(fs, 0), fb = pass_f(fs, 1), fc = pass_f(fs, 2);
            uint32_t* h2g = act + RB_H2 + (8 * w + 2 * wi) * 32 + lane;
            const uint32_t a0 = mkdesc(sb + OFF_Y + w * HALF, DT);
            if (RUN(3)) {
                uint32_t ra2, na2, rb2, nb2;
                {
                    const uint32_t* sg = act + RB_ST + ((tile * 8 + 2 * q) * 64 + 16 * wi + lr) * 2;
                    uint2 u[4];
                    do {
#pragma unroll
                        for (int i = 0; i < 4; i++) u[i] = ld_relaxed2(sg + (i >> 1) * 128 + (i & 1) * 16);
                    } while (__any_sync(~0u, min(min(min(u[0].x, u[0].y), min(u[1].x, u[1].y)), min(min(u[2].x, u[2].y), min(u[3].x, u[3].y))) == 0u) && !sc);
                    float v[4] = {__uint_as_float(u[0].x) + __uint_as_float(u[2].x), __uint_as_float(u[0].y) + __uint_as_float(u[2].y),
                                  __uint_as_float(u[1].x) + __uint_as_float(u[3].x), __uint_as_float(u[1].y) + __uint_as_float(u[3].y)};
#pragma unroll
                    for (int i = 0; i < 4; i++) { v[i] += __shfl_xor_sync(~0u, v[i], 1); v[i] += __shfl_xor_sync(~0u, v[i], 2); }
                    ln_coeffs(v[0] * (1.f / DM), v[1] * (1.f / DM), ra2, na2);
                    ln_coeffs(v[2] * (1.f / DM), v[3] * (1.f / DM), rb2, nb2);
                }
                WAIT(B_GFULL + 2 + w, 0);
                PROFC(16);
                const uint32_t ha = sb + OFF_Y + w * HALF + (lane >> 4) * 1024 + (2 * wi + ((lane >> 3) & 1)) * 128 + (lane & 7) * 16;
                const uint32_t sta = sb + M_ST + q * 16;
                const uint32_t* xg = act + RB_X1 + tile * 14336 + wi * 64 + lane;
                uint32_t x[16];
                uint4 st[4];
                uint32_t hl = ha, sl2 = sta;
                auto load = [&]() {
#pragma unroll
                    for (int i = 0; i < 4; i++) { ldsm4(hl + 2048 * i, x + 4 * i); st[i] = lds4(sl2 + 64 * i); }
                };
                float ac[128];
                uint32_t ad = a0, bd = mkdesc(sb, DB128), fb_ = BAR(B_FULL), eb_ = BAR(B_DUMMY), par = sc;
                reg_def<128>(ac);
                load();
#pragma unroll 1
                for (int s2 = -1; s2 < 7; s2++) {
#pragma unroll
                    for (int e = 0; e < 2; e++) {
                        if (s2 >= 0) {
                            mbar_wait_c(fb_, par);
                            WG_FENCE();
                            wgmma_ss_256<DT, DB128>(ac, ad, bd, (s2 | e) != 0);
                            wgmma_ss_256<DT, DB128>(ac, ad + 128, bd + 128, 1);
                            WG_COMMIT();
                        }
                        if (e == 0 && s2 < 6) {
                            uint32_t mn = x[0];
#pragma unroll
                            for (int i = 1; i < 16; i++) mn = min(mn, x[i]);
                            if (__any_sync(~0u, mn < 1u - sc)) x1_fix(x, xg + ((hl - ha) >> 2));
#pragma unroll
                            for (int i = 0; i < 4; i++)
                                stsm4(hl + 2048 * i, hfma2(hfma2(x[4 * i], ra2, na2), st[i].x, st[i].y), hfma2(hfma2(x[4 * i + 1], rb2, nb2), st[i].x, st[i].y),
                                      hfma2(hfma2(x[4 * i + 2], ra2, na2), st[i].z, st[i].w), hfma2(hfma2(x[4 * i + 3], rb2, nb2), st[i].z, st[i].w));
                        }
                        if (e == 1 && s2 < 6) {
                            fence_async_smem();
                            if (s2 == 0) mbar_wait_c(BAR(B_XFULL + 4 + w), 1);
                            if (s2 < 5) { hl += 8192; sl2 += 256; }
                            load();
                        }
                        if (s2 >= 0) {
                            WG_WAIT(1);
                            warp_arrive(eb_);
                            eb_ = fb_ + 8 * (B_EMPTY - B_FULL);
                            ad += 256; bd += 1024; fb_ += 8;
                            if (e == 0 && s2 == 3) { bd -= 7 * 1024; fb_ -= 56; par = 1; }
                        }
                    }
                }
                PROFC(18);
                WG_WAIT(0);
                reg_fence<128>(ac);
                warp_arrive(BAR(B_EMPTY + 6));
#pragma unroll
                for (int g = 0; g < 16; g++) {
                    h2a[2 * g] = hmul2(pack2_relu(ac[4 * g], ac[4 * g + 1]), pack2(ac[64 + 4 * g], ac[64 + 4 * g + 1]));
                    h2a[2 * g + 1] = hmul2(pack2_relu(ac[4 * g + 2], ac[4 * g + 3]), pack2(ac[64 + 4 * g + 2], ac[64 + 4 * g + 3]));
                    h2g[(fa / 8 + g) * 512] = h2a[2 * g]; h2g[(fa / 8 + g) * 512 + 32] = h2a[2 * g + 1];
                }
                warp_arrive(BAR(B_PUB + 6));
            } else reg_def<32>(h2a);
            PROFC(19);
            if (RUN(5)) {
                float ac[64];
                reg_def<64>(ac);
                const uint32_t bx = mkdesc(sb, dconst(8192, 1024, 1));
#pragma unroll kB
                for (int s = 0; s < 7; s++) {
                    WAIT(B_FULL + s, 0);
                    const uint32_t ad = a0 + s * 512, bd = bx + (slot_off(s) >> 4);
                    WG_FENCE();
#pragma unroll
                    for (int k = 0; k < 4; k++) wgmma_ss_128<DT, DB128>(ac, ad + k * 128, bd + k * 128, (s | k) != 0);
                    WG_COMMIT();
                    if (s > 0) { WG_WAIT(1); warp_arrive(BAR(B_EMPTY + s - 1)); }
                }
                WG_WAIT(0);
                reg_fence<64>(ac);
                warp_arrive(BAR(B_EMPTY + 6));
#pragma unroll
                for (int g = 0; g < 8; g++) {
                    h2b[2 * g] = hmul2(pack2_relu(ac[4 * g], ac[4 * g + 1]), pack2(ac[32 + 4 * g], ac[32 + 4 * g + 1]));
                    h2b[2 * g + 1] = hmul2(pack2_relu(ac[4 * g + 2], ac[4 * g + 3]), pack2(ac[32 + 4 * g + 2], ac[32 + 4 * g + 3]));
                    h2g[(fb / 8 + g) * 512] = h2b[2 * g]; h2g[(fb / 8 + g) * 512 + 32] = h2b[2 * g + 1];
                }
                warp_arrive(BAR(B_PUB + 7));
            } else reg_def<16>(h2b);
            PROFC(27);
            if (RUN(6)) {
                float ac[32];
                reg_def<32>(ac);
                const uint32_t bx = mkdesc(sb, dconst(4096, 512, 2));
#pragma unroll kC
                for (int s = 0; s < 7; s++) {
                    WAIT(B_FULL + s, 1);
                    const uint32_t ad = a0 + s * 512, bd = bx + (slot_off(s) >> 4);
                    WG_FENCE();
#pragma unroll
                    for (int k = 0; k < 4; k++) wgmma_ss_64<DT, dconst(4096, 512, 2)>(ac, ad + k * 128, bd + k * 64, (s | k) != 0);
                    WG_COMMIT();
                    if (s > 0) { WG_WAIT(1); warp_arrive(BAR(B_EMPTY + s - 1)); }
                }
                WG_WAIT(0);
                reg_fence<32>(ac);
                __syncwarp();
                if (lane < 6) mbar_arrive(BAR(B_EMPTY + 6 + lane));
                PROFC(20);
#pragma unroll
                for (int g = 0; g < 4; g++) {
                    h2b[16 + 2 * g] = hmul2(pack2_relu(ac[4 * g], ac[4 * g + 1]), pack2(ac[16 + 4 * g], ac[16 + 4 * g + 1]));
                    h2b[16 + 2 * g + 1] = hmul2(pack2_relu(ac[4 * g + 2], ac[4 * g + 3]), pack2(ac[16 + 4 * g + 2], ac[16 + 4 * g + 3]));
                    h2g[(fc / 8 + g) * 512] = h2b[16 + 2 * g]; h2g[(fc / 8 + g) * 512 + 32] = h2b[16 + 2 * g + 1];
                }
                warp_arrive(BAR(B_PUB + 8));
                asm volatile("barrier.cluster.wait.aligned;" ::: "memory");
                if (lane == 0 && !sc) {
                    uint32_t rb;
                    asm volatile("mapa.shared::cluster.u32 %0, %1, %2;" : "=r"(rb) : "r"(BAR(B_PEER)), "r"(kh ^ 1));
                    asm volatile("mbarrier.arrive.relaxed.cluster.shared::cluster.b64 _, [%0];" ::"r"(rb) : "memory");
                }
            } else reg_def<8>(h2b + 16);
        }
        PROFC(21);
        if (RUN(7)) {
            float ac[56];
            reg_def<56>(ac);
            constexpr uint64_t DAN = dconst(2048, 128, 0);
            constexpr uint64_t DW = dconst(128, 512, 0);
            const uint32_t bx = mkdesc(sb, DW);
#pragma unroll
            for (int e = 0; e < 4; e++) {
                WAIT(B_FULL + e, 0);
                const uint32_t bd = bx + (slot_off(e) >> 4);
                const uint32_t* hh = e < 2 ? h2a + 16 * e : h2b + 16 * (e - 2);
                WG_FENCE();
#pragma unroll
                for (int k = 0; k < (e < 3 ? 4 : 2); k++) wgmma_rs_112<DW>(ac, hh[4 * k], hh[4 * k + 1], hh[4 * k + 2], hh[4 * k + 3], bd + (k >> 1) * 512 + (k & 1) * 16, (e | k) != 0);
                WG_COMMIT();
                if (e > 0) { WG_WAIT(1); warp_arrive(BAR(B_EMPTY + e - 1)); }
            }
            PROFC(22);
            uint32_t ad = mkdesc(sb + 4 * 16384 + 8192 + w * 1024, DAN), bd = bx + 4 * 1024, fb_ = BAR(B_FULL + 4), eb_ = BAR(B_EMPTY + 3), par = sc;
#pragma unroll 1
            for (int e = 4; e < 25; e++) {
                mbar_wait_c(fb_, par);
                WG_FENCE();
                wgmma_ss_112<DAN, DW>(ac, ad, bd, 1);
                wgmma_ss_112<DAN, DW>(ac, ad + 256, bd + 16, 1);
                WG_COMMIT();
                WG_WAIT(1);
                warp_arrive(eb_);
                eb_ = fb_ + 8 * (B_EMPTY - B_FULL);
                ad += 1024; bd += 1024; fb_ += 8;
                if (e == 11 || e == 23) { ad -= 12 * 1024; bd -= 12 * 1024; fb_ -= 96; par = (par ^ 1) | sc; }
            }
            mbar_wait_cluster(BAR(B_PEER), sc);
            WG_WAIT(0);
            reg_fence<56>(ac);
            PROFC(24);
            uint32_t rdst, rbar;
            asm volatile("mapa.shared::cluster.u32 %0, %1, %2;" : "=r"(rdst) : "r"(sb + OFF_Y + (5 + w) * 16384 + t * 16), "r"(kh ^ 1 ^ sc));
            asm volatile("mapa.shared::cluster.u32 %0, %1, %2;" : "=r"(rbar) : "r"(BAR(B_XCH + w)), "r"(kh ^ 1 ^ sc));
#define ACG(g, i) ac[4 * (g) + (i)]
#pragma unroll
            for (int g = 0; g < 7; g++) {
                const float v0 = kh ? ACG(g, 0) : ACG(g + 7, 0), v1 = kh ? ACG(g, 1) : ACG(g + 7, 1);
                const float v2 = kh ? ACG(g, 2) : ACG(g + 7, 2), v3 = kh ? ACG(g, 3) : ACG(g + 7, 3);
                if (!sc) asm volatile("st.async.shared::cluster.mbarrier::complete_tx::bytes.v4.f32 [%0], {%1,%2,%3,%4}, [%5];"
                             ::"r"(rdst + g * 2048), "f"(v0), "f"(v1), "f"(v2), "f"(v3), "r"(rbar) : "memory");
            }
            mbar_wait_cluster(BAR(B_XCH + w), sc);
            PROFC(25);
            bf16* og = (sc ? (bf16*)act : p.out + (size_t)128 * r * DM) + (size_t)ra * DM + 56 * j + 2 * q;
#pragma unroll
            for (int g = 0; g < 7; g++) {
                const uint4 rv = *(const uint4*)(smem + OFF_Y + (5 + w) * 16384 + t * 16 + g * 2048);
                const float2 gb = *(const float2*)(smem + M_G + 224 + (8 * g + 2 * q) * 4);
                const float v0 = (kh ? ACG(g + 7, 0) : ACG(g, 0)) + __uint_as_float(rv.x), v1 = (kh ? ACG(g + 7, 1) : ACG(g, 1)) + __uint_as_float(rv.y);
                const float v2 = (kh ? ACG(g + 7, 2) : ACG(g, 2)) + __uint_as_float(rv.z), v3 = (kh ? ACG(g + 7, 3) : ACG(g, 3)) + __uint_as_float(rv.w);
                *(uint32_t*)(og + 8 * g) = pack2(fmaf(gb.x, v0, bf_lo(x1p[2 * g])), fmaf(gb.y, v1, bf_hi(x1p[2 * g])));
                *(uint32_t*)(og + 8 * DM + 8 * g) = pack2(fmaf(gb.x, v2, bf_lo(x1p[2 * g + 1])), fmaf(gb.y, v3, bf_hi(x1p[2 * g + 1])));
            }
        }
        PROFC(26);
        bar_sync(1 + w, 128);
        if (wi == 0) warp_arrive(BAR(B_DONE));
    } else {
        const int lane = fresh_tid() & 31;
        const bool early = kh == 0, gemv = r < 14;
        const int mcol = early ? 16 * (4 * r + nq) : 2 * DM + 32 * (4 * r + nq);
        const uint32_t wmbuf = sb + OFF_Y + HALF;
        asm volatile("setmaxnreg.dec.sync.aligned.u32 56;");
        if (warp == 9) {
#pragma unroll
            for (int i = 56; i < 64; i++) init_e(BAR(i), 1);
            fence_async_smem();
        }
        if (warp == 8) { init_e(BAR(B_WMFULL), 2); fence_async_smem(); }
        bar_arrive(0, 384);
        asm volatile("barrier.cluster.arrive.relaxed.aligned;" ::: "memory");
        uint32_t target = 0;
        if (warp == 8) {
            if (!sc) {
                expect_e(BAR(B_WMFULL), gemv ? 28672 >> early : 0);
                if (early && gemv) { tma3_e(wmbuf, &p.wm, mcol, 0, 0, BAR(B_WMFULL)); tma3_e(wmbuf + 7168, &p.wm, mcol, 224, 0, BAR(B_WMFULL)); }
#pragma unroll 1
                for (int kb = 0; kb < 7; kb++) {
                    expect_e(BAR(B_XFULL + kb), 16384);
                    tma3_e(sb + OFF_X + kb * 16384, &p.xm, 64 * kb, 128 * r, 0, BAR(B_XFULL + kb));
                }
            }
#pragma unroll 1
            for (int mt = 0; mt < 4; mt++) {
                if (mt == 1) {
                    if (!early && gemv) {
#pragma unroll 1
                        for (int k = 0; k < 4; k++) tma3_e(wmbuf + k * 7168, &p.wm, mcol + (k >> 1) * 16, (k & 1) * 224, 0, BAR(B_WMFULL));
                    }
                    bar_sync(9, 384);
                    if (sc) return;
                    mbar_wait(BAR(B_MOD1), 0);
                    mbar_wait(BAR(B_WMFREE), 0);
                }
                if (mt == 2) mbar_wait(BAR(B_XFREE), 0);
                if (mt == 3) mbar_wait(BAR(B_VRFULL), 0);
                const uint32_t bar = BAR(mt == 3 ? B_WOFULL : B_FULLK + mt), dst = sb + (mt < 2 ? OFF_Y : OFF_X) + (mt & 1) * HALF;
                const int c0 = (mt < 2 ? DM + DM * mt : 0) + 56 * j - 8 * kh;
                if (!sc) {
                    expect_e(bar, HALF);
                    tma3_e(dst, mt == 3 ? &p.wo : &p.qkv, c0, 0, 0, bar);
                    tma3_e(dst + HALF / 2, mt == 3 ? &p.wo : &p.qkv, c0, 224, 0, bar);
                }
            }
            expect_e(BAR(B_XCH), 14336);
            expect_e(BAR(B_XCH + 1), 14336);
        } else {
            if (warp == 10 && !sc) {
                l2_prefetch_e((const char*)p.wqkv + (size_t)b * 9408, 9408);
                if (lane == 0) sts1(sb + M_EPOCH, atomicAdd(&g_ticket, 1u) / NCTA);
            }
            if (warp == 11) {
#pragma unroll
                for (int i = 0; i < 8; i++) {
                    const int wd = lane + 32 * i;
                    const uint32_t cb = i < 7 ? __ldg((const uint32_t*)p.c + wd) : 0u;
                    sts1(wmbuf + 28672 + (wd >> 3) * 32 + (wd & 3) * 8 + (wd & 4), pack2(silu_bf(cb & 0xFFFFu), silu_bf(cb >> 16)));
                }
            }
            bar_sync(9, 384);
            if (sc) return;
            target = lds1(sb + M_EPOCH) + 1;
            const uint32_t tag = target & 0xFFFFu;
            if (warp == 11) {
                warp_arrive(BAR(B_WMFULL));
                mbar_wait(BAR(B_GEMV), 0);
                float sum = 0.f;
#pragma unroll
                for (int i = 0; i < 8; i++) sum += *(const float*)(smem + OFF_Y + HALF + 29696 + (i * 32 + (early ? lane & 15 : lane)) * 4);
                const uint32_t word = (pack2(sum, 0.f) << 16) | tag;
                if (gemv) {
                    uint32_t* mg = g_mod + mcol + (early ? (lane & 15) + (lane >> 4) * 4 * 6 * DM : lane);
#pragma unroll
                    for (int i = 0; i < 8; i++) if (i < 4 || !early) st_relaxed(mg + i * 6 * DM, word);
                }
                warp_arrive(BAR(B_WMFREE));
            }
            const uint4* modp = (const uint4*)g_mod + (r & 7) * (6 * DM / 4);
            const bool p2 = warp == 11;
            mbar_wait(BAR(p2 ? B_PUB : B_XFULL + 4), 0);
#pragma unroll 1
            for (int it = p2 ? 0 : warp - 9; it < (p2 ? 2 : warp - 8); it++) {
                const int i0 = lane + 32 * it, imax = p2 ? 251 : 223;
                uint4 v[4];
#pragma unroll 1
                for (int n = 0;; n++) {
                    uint32_t bad = 0;
#pragma unroll
                    for (int k = 0; k < 4; k++) {
                        const int i = min(i0 + 64 * k, imax);
                        v[k] = ld_relaxed4(modp + (i < 224 ? (p2 ? 336 : 0) + i : (i < 238 ? 14 * j + i : 14 * j + i + 322)));
                        bad |= (v[k].x ^ tag) | (v[k].y ^ tag) | (v[k].z ^ tag) | (v[k].w ^ tag);
                    }
                    if (!__any_sync(~0u, bad & 0xFFFFu)) break;
                    if (n > SPIN_LIMIT) __trap();
                }
#pragma unroll
                for (int k = 0; k < 4; k++) {
                    const int i = min(i0 + 64 * k, imax);
                    if (i < 224) {
                        const int isc = i >= 112, c4 = i - 112 * isc;
                        const float one = isc ? 1.f : 0.f;
                        const uint32_t a = sb + M_ST + (c4 >> 2) * 64 + (c4 & 1) * 32 + (c4 & 2) * 4 + (isc ? 0 : 4);
                        sts1(a, pack2(bf_hi(v[k].x) + one, bf_hi(v[k].y) + one));
                        sts1(a + 16, pack2(bf_hi(v[k].z) + one, bf_hi(v[k].w) + one));
                    } else {
                        sts4(sb + M_G + (i - 224) * 16, make_uint4(v[k].x & 0xFFFF0000u, v[k].y & 0xFFFF0000u, v[k].z & 0xFFFF0000u, v[k].w & 0xFFFF0000u));
                    }
                }
                warp_arrive(BAR(p2 ? B_MOD2 : B_MOD1));
            }
            if (warp == 9) {
#pragma unroll 1
                for (int kv = 0; kv < 2; kv++) {
                    mbar_wait(BAR(B_PUB + kv), 0);
                    wait_flags(g_flag + b * 128 + lane, target, (r >= 2 ? 6u : r == 1 ? 2u : 0u) << (8 * kv));
                    fence_async_global();
                    const uint32_t dst = sb + OFF_Y + (kv ? Y_VR : Y_K);
                    expect_e(BAR(B_KRFULL + kv), r >= 2 ? 28672 : r == 1 ? 14336 : 0);
                    if (r >= 2) bulk_e(dst, act - 2 * RB_WORDS + RB_KV + j * 7168 + kv * 3584, 14336, BAR(B_KRFULL + kv));
                    if (r >= 1) bulk_e(dst + 14336, act - RB_WORDS + RB_KV + j * 7168 + kv * 3584, 14336, BAR(B_KRFULL + kv));
                }
            } else if (warp == 11) {
                mbar_wait(BAR(B_VRFULL), 0);
                l2_prefetch_e((const char*)p.wg + (size_t)b * 12544, 12544);
                l2_prefetch_e((const char*)p.wu + (size_t)b * 12544, 12544);
#pragma unroll 1
                for (int k = 0; k < (r < 12 ? 2 : 1); k++) {
                    const int u = 28 * kh + r + 16 * k;
                    expect_e(BAR(B_XFULL + k), 7168);
                    tma3_e(sb + OFF_Y + 102400, &p.dn, 0, 32 * u, 14 * nq, BAR(B_XFULL + k));
                    mbar_wait(BAR(B_XFULL + k), 1);
                    asm volatile("{\n.reg .pred p;\nelect.sync _|p, 0xffffffff;\n@p cp.async.bulk.global.shared::cta.bulk_group [%0], [%1], 7168;\n"
                                 "cp.async.bulk.commit_group;\ncp.async.bulk.wait_group 0;\n}" ::"l"(g_wd + (size_t)(u * 4 + nq) * 1792), "r"(sb + OFF_Y + 102400) : "memory");
                    __syncwarp();
                }
                warp_arrive(BAR(B_WMFREE));
                fence_gpu();
                if (lane < 16) st_relaxed(g_flag + (8 * lane + j) * 128 + 96 + r, target);
            }
        }
        if (warp == 8 || warp == 11) {
            const int sec = warp == 11;
            if (sec) ring_loader<1>(p, sb, r, j, lane); else ring_loader<0>(p, sb, r, j, lane);
            mbar_wait(BAR(B_DONE), 0);
        } else if (warp == 9) {
#pragma unroll
            for (int ev = 0; ev < 4; ev++) { expect_e(BAR(B_GFULL + ev), ev < 2 ? HALF / 2 : 16384); expect_e(BAR(B_XFULL + 2 + ev), ev < 2 ? HALF / 2 : HALF - 16384); }
            mbar_wait(BAR(B_PUB + 2), 0);
            const uint32_t* fp = g_flag + b * 128 + 32 + lane;
            const int par = (target - 1) & 1;
#pragma unroll 1
            for (int n = 0, ev = 0; ev < 4; n++) {
                if (ev == 1) { mbar_wait(BAR(B_WMFREE), 1); mbar_wait(BAR(B_PUB + 3), 0); }
                uint32_t ok = __ballot_sync(~0u, (int)(ld_relaxed(fp) - target) >= 0) >> (8 * ev);
                while ((ok & 0xFFu) == 0xFFu) {
                    asm volatile("fence.acquire.gpu;" ::: "memory");
                    fence_async_global();
                    const int tile = (ev & 1) + (ev >> 1) * par * 2;
                    const uint32_t dst = sb + (ev == 0 ? OFF_X : OFF_Y + (ev & 1) * HALF), first = ev < 2 ? HALF / 2 : 16384;
                    const char* src = (const char*)(act + RB_O + ((ev >> 1) * 2 + tile) * 14336);
                    bulk_e(dst, src, first, BAR(B_GFULL + ev));
                    bulk_e(dst + first, src + first, HALF - first, BAR(B_XFULL + 2 + ev));
                    if (ev) PROFH(4 + ev);
                    ev++; ok >>= 8;
                }
                if (n > SPIN_LIMIT) __trap();
            }
            mbar_wait(BAR(B_XFULL + 5), 1);
#pragma unroll 1
            for (int hf = 0; hf < 2; hf++) {
                const int tile = (par ^ 1) * 2 + hf;
                uint4* xz = (uint4*)(act + RB_X1 + tile * 14336 + j * 1792) + lane;
#pragma unroll
                for (int i = 0; i < 14; i++) xz[i * 32] = make_uint4(0, 0, 0, 0);
                ((uint4*)(act + RB_ST + (tile * 8 + j) * 128))[lane] = make_uint4(0, 0, 0, 0);
            }
#pragma unroll 1
            for (int ps = 0; ps < 3; ps++) {
                mbar_wait(BAR(B_PUB + 6 + ps), 0);
                wait_flags(g_flag + b * 128 + 64 + lane, target, (0x55u << kh) << (8 * ps));
                warp_arrive(BAR(B_HRDY + ps));
                PROFH(9 + ps);
            }
        } else {
#pragma unroll 1
            for (int k = 0; k < 9; k++) {
                uint32_t* fp = k < 2 ? g_flag + (b + 8 * lane) * 128 + k * 8 + lane : g_flag + (8 * r + lane) * 128 + 16 + k * 8 + j;
                mbar_wait(BAR(B_PUB + k), 0);
                if (k != 4 && k != 5) fence_gpu();
                if (k < 2 ? (lane == 1 || lane == 2) : lane < 8) st_relaxed(fp, target);
                if (k >= 3 && k <= 5) PROFH(k - 3);
            }
        }
    }
}

#undef act
typedef CUresult (*EncodeFn)(CUtensorMap*, CUtensorMapDataType, cuuint32_t, void*, const cuuint64_t*, const cuuint64_t*, const cuuint32_t*,
                             const cuuint32_t*, CUtensorMapInterleave, CUtensorMapSwizzle, CUtensorMapL2promotion, CUtensorMapFloatOOBfill);

static void make_map(EncodeFn fn, CUtensorMap* m, const void* ptr, uint64_t d0, uint64_t d1, uint64_t d2, uint64_t s1, uint64_t s2,
                     uint32_t b0, uint32_t b1, uint32_t b2, CUtensorMapSwizzle sw) {
    cuuint64_t dims[3] = {d0, d1, d2}, strides[2] = {s1, s2};
    cuuint32_t box[3] = {b0, b1, b2}, es[3] = {1, 1, 1};
    CUresult rc = fn(m, CU_TENSOR_MAP_DATA_TYPE_BFLOAT16, 3, (void*)ptr, dims, strides, box, es, CU_TENSOR_MAP_INTERLEAVE_NONE, sw,
                     CU_TENSOR_MAP_L2_PROMOTION_L2_128B, CU_TENSOR_MAP_FLOAT_OOB_FILL_NONE);
    (void)rc;
}

extern "C" void kernel_launch(void* const* d_in, const int* in_sizes, int n_in, void* d_out, int out_size) {
    (void)in_sizes; (void)n_in; (void)out_size;
    static EncodeFn fn = nullptr;
    static uint32_t* act_base = nullptr;
    if (!fn) {
        cudaDriverEntryPointQueryResult st;
        cudaGetDriverEntryPoint("cuTensorMapEncodeTiled", (void**)&fn, cudaEnableDefault, &st);
        void* a = nullptr;
        cudaGetSymbolAddress(&a, g_act);
        act_base = (uint32_t*)(((uintptr_t)a + 0xFFFFF) & ~(uintptr_t)0xFFFFF);
        cudaFuncSetAttribute(fused_block_kernel, cudaFuncAttributeMaxDynamicSharedMemorySize, SMEM_BYTES);
    }
    Params p;
    p.x = (const bf16*)d_in[0];
    const bf16* wqkv = (const bf16*)d_in[1];
    p.wqkv = wqkv;
    p.wop = (const bf16*)d_in[2];
    p.wg = (const bf16*)d_in[4];
    p.wu = (const bf16*)d_in[5];
    p.wd = (const bf16*)d_in[6];
    p.c = (const bf16*)d_in[7];
    p.wmod = (const bf16*)d_in[8];
    p.out = (bf16*)d_out;
    p.zero = 0;
    p.actb = act_base;
    make_map(fn, &p.wm, p.wmod, 2688, 448, 1, 5376, 5376 * 448, 16, 224, 1, CU_TENSOR_MAP_SWIZZLE_NONE);
    make_map(fn, &p.xm, p.x, 448, 2048, 1, 896, 896 * 2048, 64, 128, 1, CU_TENSOR_MAP_SWIZZLE_128B);
    make_map(fn, &p.qkv, wqkv, 1344, 448, 1, 2688, 2688 * 448, 64, 224, 1, CU_TENSOR_MAP_SWIZZLE_128B);
    make_map(fn, &p.wo, p.wop, 448, 448, 1, 896, 896 * 448, 64, 224, 1, CU_TENSOR_MAP_SWIZZLE_128B);
    make_map(fn, &p.ga, p.wg, 64, 448, 28, 3584, 128, 64, 32, 2, CU_TENSOR_MAP_SWIZZLE_128B);
    make_map(fn, &p.ua, p.wu, 64, 448, 28, 3584, 128, 64, 32, 2, CU_TENSOR_MAP_SWIZZLE_128B);
    make_map(fn, &p.gb, p.wg, 64, 448, 28, 3584, 128, 64, 64, 1, CU_TENSOR_MAP_SWIZZLE_128B);
    make_map(fn, &p.ub, p.wu, 64, 448, 28, 3584, 128, 64, 64, 1, CU_TENSOR_MAP_SWIZZLE_128B);
    make_map(fn, &p.gc, p.wg, 32, 448, 56, 3584, 64, 32, 64, 1, CU_TENSOR_MAP_SWIZZLE_64B);
    make_map(fn, &p.uc, p.wu, 32, 448, 56, 3584, 64, 32, 64, 1, CU_TENSOR_MAP_SWIZZLE_64B);
    make_map(fn, &p.dn, p.wd, 8, 1792, 56, 896, 16, 8, 32, 14, CU_TENSOR_MAP_SWIZZLE_NONE);
    fused_block_kernel<<<GRID, 384, SMEM_BYTES>>>(p);
}
```

```cpp
#include <cuda_runtime.h>
#include <cuda_bf16.h>
#include <cuda.h>
#include <stdint.h>

typedef __nv_bfloat16 bf16;

template<uint64_t CB> __device__ __forceinline__ void wgmma_rs_56(float* d, uint32_t a0, uint32_t a1, uint32_t a2, uint32_t a3, uint32_t db, int sd) {
  asm volatile("{\n.reg .pred p;\n.reg .b64 b;\nsetp.ne.b32 p, %33, 0;\nmov.b64 b, {%32, %34};\n"
    "wgmma.mma_async.sync.aligned.m64n56k16.f32.bf16.bf16 {%0,%1,%2,%3,%4,%5,%6,%7,%8,%9,%10,%11,%12,%13,%14,%15,%16,%17,%18,%19,%20,%21,%22,%23,%24,%25,%26,%27}, {%28,%29,%30,%31}, b, p, 1, 1, 1;\n}\n"
    : "+f"(d[0]),"+f"(d[1]),"+f"(d[2]),"+f"(d[3]),"+f"(d[4]),"+f"(d[5]),"+f"(d[6]),"+f"(d[7]),"+f"(d[8]),"+f"(d[9]),"+f"(d[10]),"+f"(d[11]),"+f"(d[12]),"+f"(d[13]),"+f"(d[14]),"+f"(d[15]),"+f"(d[16]),"+f"(d[17]),"+f"(d[18]),"+f"(d[19]),"+f"(d[20]),"+f"(d[21]),"+f"(d[22]),"+f"(d[23]),"+f"(d[24]),"+f"(d[25]),"+f"(d[26]),"+f"(d[27])
    : "r"(a0), "r"(a1), "r"(a2), "r"(a3), "r"(db), "r"(sd), "n"((uint32_t)(CB >> 32)));
}
template<uint64_t CA, uint64_t CB> __device__ __forceinline__ void wgmma_ss_56(float* d, uint32_t da, uint32_t db, int sd) {
  asm volatile("{\n.reg .pred p;\n.reg .b64 a, b;\nsetp.ne.b32 p, %30, 0;\nmov.b64 a, {%28, %31};\nmov.b64 b, {%29, %32};\n"
    "wgmma.mma_async.sync.aligned.m64n56k16.f32.bf16.bf16 {%0,%1,%2,%3,%4,%5,%6,%7,%8,%9,%10,%11,%12,%13,%14,%15,%16,%17,%18,%19,%20,%21,%22,%23,%24,%25,%26,%27}, a, b, p, 1, 1, 0, 1;\n}\n"
    : "+f"(d[0]),"+f"(d[1]),"+f"(d[2]),"+f"(d[3]),"+f"(d[4]),"+f"(d[5]),"+f"(d[6]),"+f"(d[7]),"+f"(d[8]),"+f"(d[9]),"+f"(d[10]),"+f"(d[11]),"+f"(d[12]),"+f"(d[13]),"+f"(d[14]),"+f"(d[15]),"+f"(d[16]),"+f"(d[17]),"+f"(d[18]),"+f"(d[19]),"+f"(d[20]),"+f"(d[21]),"+f"(d[22]),"+f"(d[23]),"+f"(d[24]),"+f"(d[25]),"+f"(d[26]),"+f"(d[27])
    : "r"(da), "r"(db), "r"(sd), "n"((uint32_t)(CA >> 32)), "n"((uint32_t)(CB >> 32)));
}
template<uint64_t CB> __device__ __forceinline__ void wgmma_rs_256(float* d, uint32_t a0, uint32_t a1, uint32_t a2, uint32_t a3, uint32_t db, int sd) {
  asm volatile("{\n.reg .pred p;\n.reg .b64 b;\nsetp.ne.b32 p, %133, 0;\nmov.b64 b, {%132, %134};\n"
    "wgmma.mma_async.sync.aligned.m64n256k16.f32.bf16.bf16 {%0,%1,%2,%3,%4,%5,%6,%7,%8,%9,%10,%11,%12,%13,%14,%15,%16,%17,%18,%19,%20,%21,%22,%23,%24,%25,%26,%27,%28,%29,%30,%31,%32,%33,%34,%35,%36,%37,%38,%39,%40,%41,%42,%43,%44,%45,%46,%47,%48,%49,%50,%51,%52,%53,%54,%55,%56,%57,%58,%59,%60,%61,%62,%63,%64,%65,%66,%67,%68,%69,%70,%71,%72,%73,%74,%75,%76,%77,%78,%79,%80,%81,%82,%83,%84,%85,%86,%87,%88,%89,%90,%91,%92,%93,%94,%95,%96,%97,%98,%99,%100,%101,%102,%103,%104,%105,%106,%107,%108,%109,%110,%111,%112,%113,%114,%115,%116,%117,%118,%119,%120,%121,%122,%123,%124,%125,%126,%127}, {%128,%129,%130,%131}, b, p, 1, 1, 1;\n}\n"
    : "+f"(d[0]),"+f"(d[1]),"+f"(d[2]),"+f"(d[3]),"+f"(d[4]),"+f"(d[5]),"+f"(d[6]),"+f"(d[7]),"+f"(d[8]),"+f"(d[9]),"+f"(d[10]),"+f"(d[11]),"+f"(d[12]),"+f"(d[13]),"+f"(d[14]),"+f"(d[15]),"+f"(d[16]),"+f"(d[17]),"+f"(d[18]),"+f"(d[19]),"+f"(d[20]),"+f"(d[21]),"+f"(d[22]),"+f"(d[23]),"+f"(d[24]),"+f"(d[25]),"+f"(d[26]),"+f"(d[27]),"+f"(d[28]),"+f"(d[29]),"+f"(d[30]),"+f"(d[31]),"+f"(d[32]),"+f"(d[33]),"+f"(d[34]),"+f"(d[35]),"+f"(d[36]),"+f"(d[37]),"+f"(d[38]),"+f"(d[39]),"+f"(d[40]),"+f"(d[41]),"+f"(d[42]),"+f"(d[43]),"+f"(d[44]),"+f"(d[45]),"+f"(d[46]),"+f"(d[47]),"+f"(d[48]),"+f"(d[49]),"+f"(d[50]),"+f"(d[51]),"+f"(d[52]),"+f"(d[53]),"+f"(d[54]),"+f"(d[55]),"+f"(d[56]),"+f"(d[57]),"+f"(d[58]),"+f"(d[59]),"+f"(d[60]),"+f"(d[61]),"+f"(d[62]),"+f"(d[63]),"+f"(d[64]),"+f"(d[65]),"+f"(d[66]),"+f"(d[67]),"+f"(d[68]),"+f"(d[69]),"+f"(d[70]),"+f"(d[71]),"+f"(d[72]),"+f"(d[73]),"+f"(d[74]),"+f"(d[75]),"+f"(d[76]),"+f"(d[77]),"+f"(d[78]),"+f"(d[79]),"+f"(d[80]),"+f"(d[81]),"+f"(d[82]),"+f"(d[83]),"+f"(d[84]),"+f"(d[85]),"+f"(d[86]),"+f"(d[87]),"+f"(d[88]),"+f"(d[89]),"+f"(d[90]),"+f"(d[91]),"+f"(d[92]),"+f"(d[93]),"+f"(d[94]),"+f"(d[95]),"+f"(d[96]),"+f"(d[97]),"+f"(d[98]),"+f"(d[99]),"+f"(d[100]),"+f"(d[101]),"+f"(d[102]),"+f"(d[103]),"+f"(d[104]),"+f"(d[105]),"+f"(d[106]),"+f"(d[107]),"+f"(d[108]),"+f"(d[109]),"+f"(d[110]),"+f"(d[111]),"+f"(d[112]),"+f"(d[113]),"+f"(d[114]),"+f"(d[115]),"+f"(d[116]),"+f"(d[117]),"+f"(d[118]),"+f"(d[119]),"+f"(d[120]),"+f"(d[121]),"+f"(d[122]),"+f"(d[123]),"+f"(d[124]),"+f"(d[125]),"+f"(d[126]),"+f"(d[127])
    : "r"(a0), "r"(a1), "r"(a2), "r"(a3), "r"(db), "r"(sd), "n"((uint32_t)(CB >> 32)));
}
template<uint64_t CA, uint64_t CB> __device__ __forceinline__ void wgmma_ss_128(float* d, uint32_t da, uint32_t db, int sd) {
  asm volatile("{\n.reg .pred p;\n.reg .b64 a, b;\nsetp.ne.b32 p, %66, 0;\nmov.b64 a, {%64, %67};\nmov.b64 b, {%65, %68};\n"
    "wgmma.mma_async.sync.aligned.m64n128k16.f32.bf16.bf16 {%0,%1,%2,%3,%4,%5,%6,%7,%8,%9,%10,%11,%12,%13,%14,%15,%16,%17,%18,%19,%20,%21,%22,%23,%24,%25,%26,%27,%28,%29,%30,%31,%32,%33,%34,%35,%36,%37,%38,%39,%40,%41,%42,%43,%44,%45,%46,%47,%48,%49,%50,%51,%52,%53,%54,%55,%56,%57,%58,%59,%60,%61,%62,%63}, a, b, p, 1, 1, 0, 1;\n}\n"
    : "+f"(d[0]),"+f"(d[1]),"+f"(d[2]),"+f"(d[3]),"+f"(d[4]),"+f"(d[5]),"+f"(d[6]),"+f"(d[7]),"+f"(d[8]),"+f"(d[9]),"+f"(d[10]),"+f"(d[11]),"+f"(d[12]),"+f"(d[13]),"+f"(d[14]),"+f"(d[15]),"+f"(d[16]),"+f"(d[17]),"+f"(d[18]),"+f"(d[19]),"+f"(d[20]),"+f"(d[21]),"+f"(d[22]),"+f"(d[23]),"+f"(d[24]),"+f"(d[25]),"+f"(d[26]),"+f"(d[27]),"+f"(d[28]),"+f"(d[29]),"+f"(d[30]),"+f"(d[31]),"+f"(d[32]),"+f"(d[33]),"+f"(d[34]),"+f"(d[35]),"+f"(d[36]),"+f"(d[37]),"+f"(d[38]),"+f"(d[39]),"+f"(d[40]),"+f"(d[41]),"+f"(d[42]),"+f"(d[43]),"+f"(d[44]),"+f"(d[45]),"+f"(d[46]),"+f"(d[47]),"+f"(d[48]),"+f"(d[49]),"+f"(d[50]),"+f"(d[51]),"+f"(d[52]),"+f"(d[53]),"+f"(d[54]),"+f"(d[55]),"+f"(d[56]),"+f"(d[57]),"+f"(d[58]),"+f"(d[59]),"+f"(d[60]),"+f"(d[61]),"+f"(d[62]),"+f"(d[63])
    : "r"(da), "r"(db), "r"(sd), "n"((uint32_t)(CA >> 32)), "n"((uint32_t)(CB >> 32)));
}
template<uint64_t CA, uint64_t CB> __device__ __forceinline__ void wgmma_ss_64(float* d, uint32_t da, uint32_t db, int sd) {
  asm volatile("{\n.reg .pred p;\n.reg .b64 a, b;\nsetp.ne.b32 p, %34, 0;\nmov.b64 a, {%32, %35};\nmov.b64 b, {%33, %36};\n"
    "wgmma.mma_async.sync.aligned.m64n64k16.f32.bf16.bf16 {%0,%1,%2,%3,%4,%5,%6,%7,%8,%9,%10,%11,%12,%13,%14,%15,%16,%17,%18,%19,%20,%21,%22,%23,%24,%25,%26,%27,%28,%29,%30,%31}, a, b, p, 1, 1, 0, 1;\n}\n"
    : "+f"(d[0]),"+f"(d[1]),"+f"(d[2]),"+f"(d[3]),"+f"(d[4]),"+f"(d[5]),"+f"(d[6]),"+f"(d[7]),"+f"(d[8]),"+f"(d[9]),"+f"(d[10]),"+f"(d[11]),"+f"(d[12]),"+f"(d[13]),"+f"(d[14]),"+f"(d[15]),"+f"(d[16]),"+f"(d[17]),"+f"(d[18]),"+f"(d[19]),"+f"(d[20]),"+f"(d[21]),"+f"(d[22]),"+f"(d[23]),"+f"(d[24]),"+f"(d[25]),"+f"(d[26]),"+f"(d[27]),"+f"(d[28]),"+f"(d[29]),"+f"(d[30]),"+f"(d[31])
    : "r"(da), "r"(db), "r"(sd), "n"((uint32_t)(CA >> 32)), "n"((uint32_t)(CB >> 32)));
}
template<uint64_t CA, uint64_t CB> __device__ __forceinline__ void wgmma_ss_112(float* d, uint32_t da, uint32_t db, int sd) {
  asm volatile("{\n.reg .pred p;\n.reg .b64 a, b;\nsetp.ne.b32 p, %58, 0;\nmov.b64 a, {%56, %59};\nmov.b64 b, {%57, %60};\n"
    "wgmma.mma_async.sync.aligned.m64n112k16.f32.bf16.bf16 {%0,%1,%2,%3,%4,%5,%6,%7,%8,%9,%10,%11,%12,%13,%14,%15,%16,%17,%18,%19,%20,%21,%22,%23,%24,%25,%26,%27,%28,%29,%30,%31,%32,%33,%34,%35,%36,%37,%38,%39,%40,%41,%42,%43,%44,%45,%46,%47,%48,%49,%50,%51,%52,%53,%54,%55}, a, b, p, 1, 1, 0, 1;\n}\n"
    : "+f"(d[0]),"+f"(d[1]),"+f"(d[2]),"+f"(d[3]),"+f"(d[4]),"+f"(d[5]),"+f"(d[6]),"+f"(d[7]),"+f"(d[8]),"+f"(d[9]),"+f"(d[10]),"+f"(d[11]),"+f"(d[12]),"+f"(d[13]),"+f"(d[14]),"+f"(d[15]),"+f"(d[16]),"+f"(d[17]),"+f"(d[18]),"+f"(d[19]),"+f"(d[20]),"+f"(d[21]),"+f"(d[22]),"+f"(d[23]),"+f"(d[24]),"+f"(d[25]),"+f"(d[26]),"+f"(d[27]),"+f"(d[28]),"+f"(d[29]),"+f"(d[30]),"+f"(d[31]),"+f"(d[32]),"+f"(d[33]),"+f"(d[34]),"+f"(d[35]),"+f"(d[36]),"+f"(d[37]),"+f"(d[38]),"+f"(d[39]),"+f"(d[40]),"+f"(d[41]),"+f"(d[42]),"+f"(d[43]),"+f"(d[44]),"+f"(d[45]),"+f"(d[46]),"+f"(d[47]),"+f"(d[48]),"+f"(d[49]),"+f"(d[50]),"+f"(d[51]),"+f"(d[52]),"+f"(d[53]),"+f"(d[54]),"+f"(d[55])
    : "r"(da), "r"(db), "r"(sd), "n"((uint32_t)(CA >> 32)), "n"((uint32_t)(CB >> 32)));
}
template<uint64_t CB> __device__ __forceinline__ void wgmma_rs_112(float* d, uint32_t a0, uint32_t a1, uint32_t a2, uint32_t a3, uint32_t db, int sd) {
  asm volatile("{\n.reg .pred p;\n.reg .b64 b;\nsetp.ne.b32 p, %61, 0;\nmov.b64 b, {%60, %62};\n"
    "wgmma.mma_async.sync.aligned.m64n112k16.f32.bf16.bf16 {%0,%1,%2,%3,%4,%5,%6,%7,%8,%9,%10,%11,%12,%13,%14,%15,%16,%17,%18,%19,%20,%21,%22,%23,%24,%25,%26,%27,%28,%29,%30,%31,%32,%33,%34,%35,%36,%37,%38,%39,%40,%41,%42,%43,%44,%45,%46,%47,%48,%49,%50,%51,%52,%53,%54,%55}, {%56,%57,%58,%59}, b, p, 1, 1, 1;\n}\n"
    : "+f"(d[0]),"+f"(d[1]),"+f"(d[2]),"+f"(d[3]),"+f"(d[4]),"+f"(d[5]),"+f"(d[6]),"+f"(d[7]),"+f"(d[8]),"+f"(d[9]),"+f"(d[10]),"+f"(d[11]),"+f"(d[12]),"+f"(d[13]),"+f"(d[14]),"+f"(d[15]),"+f"(d[16]),"+f"(d[17]),"+f"(d[18]),"+f"(d[19]),"+f"(d[20]),"+f"(d[21]),"+f"(d[22]),"+f"(d[23]),"+f"(d[24]),"+f"(d[25]),"+f"(d[26]),"+f"(d[27]),"+f"(d[28]),"+f"(d[29]),"+f"(d[30]),"+f"(d[31]),"+f"(d[32]),"+f"(d[33]),"+f"(d[34]),"+f"(d[35]),"+f"(d[36]),"+f"(d[37]),"+f"(d[38]),"+f"(d[39]),"+f"(d[40]),"+f"(d[41]),"+f"(d[42]),"+f"(d[43]),"+f"(d[44]),"+f"(d[45]),"+f"(d[46]),"+f"(d[47]),"+f"(d[48]),"+f"(d[49]),"+f"(d[50]),"+f"(d[51]),"+f"(d[52]),"+f"(d[53]),"+f"(d[54]),"+f"(d[55])
    : "r"(a0), "r"(a1), "r"(a2), "r"(a3), "r"(db), "r"(sd), "n"((uint32_t)(CB >> 32)));
}

constexpr int DM = 448;
constexpr int NCTA = 128;
#define MAPPING 1
#define GRID 132
#define PINGPONG 0
#define WIN 6
#define WIN_END 25
#define UNR_B 1
#define UNR_C 1
constexpr int kB = UNR_B, kC = UNR_C;
#define MAP_S 4
constexpr int SPIN_LIMIT = 1 << 22;

constexpr uint32_t OFF_X = 0, OFF_Y = 114688, OFF_MISC = 229376, SMEM_BYTES = 232448;
constexpr uint32_t Y_VR = 0, Y_K = 28672, Y_KOWN = 57344, Y_VOWN = 71680, Y_Q = 86016;
constexpr uint32_t HALF = 57344;
constexpr uint32_t X_STAT = 49152;
constexpr uint32_t M_BAR = OFF_MISC;
constexpr uint32_t M_ST = OFF_MISC + 512;
constexpr uint32_t M_G = OFF_MISC + 2304;
constexpr uint32_t M_EPOCH = OFF_MISC + 3040;
enum { B_XFULL = 0, B_FULLK = 7, B_FULLV = 8, B_FULLQ, B_KRFULL, B_VRFULL, B_WOFULL, B_XCH, B_FULL = 16, B_MOD1 = 28, B_MOD2, B_WMFULL,
       B_EMPTY = 32, B_XFREE = B_EMPTY + 12, B_GEMV, B_PEER,
       B_PUB = 47,
       B_WMFREE = 56, B_HRDY, B_GFULL = B_HRDY + 3, B_DONE = 31, B_DUMMY = B_GEMV };

__device__ uint32_t g_ticket;
__device__ __align__(128) uint32_t g_mod[8 * 6 * DM];
__device__ __align__(128) uint32_t g_flag[144 * 128];
constexpr int RB_WORDS = 262144, RB_KV = 0, RB_O = 57344, RB_X1 = 86016, RB_H2 = 143360, RB_ST = 258048;
__device__ __align__(128) uint32_t g_act[18 * RB_WORDS];
__device__ __align__(128) uint32_t g_wd[56 * 4 * 1792];
#define PROFH(id)
#define PROFH1(id)
#define PROFC(id)

struct alignas(64) Params {
    CUtensorMap wm, xm, qkv, wo, ga, ua, gb, ub, gc, uc, dn;
    const bf16 *x, *c, *wqkv, *wmod, *wg, *wu, *wd, *wop;
    bf16* out;
    uint32_t* actb;
    uint32_t zero;
};

__device__ __forceinline__ void mbar_init(uint32_t bar, int cnt) { asm volatile("mbarrier.init.shared::cta.b64 [%0], %1;" ::"r"(bar), "r"(cnt) : "memory"); }
__device__ __forceinline__ void mbar_expect_tx(uint32_t bar, uint32_t bytes) { asm volatile("mbarrier.arrive.expect_tx.shared::cta.b64 _, [%0], %1;" ::"r"(bar), "r"(bytes) : "memory"); }
__device__ __forceinline__ void mbar_arrive(uint32_t bar) { asm volatile("mbarrier.arrive.shared::cta.b64 _, [%0];" ::"r"(bar) : "memory"); }
__device__ __forceinline__ void mbar_wait(uint32_t bar, uint32_t parity) {
    uint32_t ok; int n = 0;
    do {
        asm volatile("{\n.reg .pred p;\nmbarrier.try_wait.parity.shared::cta.b64 p, [%1], %2;\nselp.u32 %0, 1, 0, p;\n}" : "=r"(ok) : "r"(bar), "r"(parity) : "memory");
        if (++n > SPIN_LIMIT) __trap();
    } while (!ok);
}
__device__ __forceinline__ void mbar_wait_c(uint32_t bar, uint32_t parity) {
    asm volatile("{\n.reg .pred p;\nWL:\nmbarrier.try_wait.parity.shared::cta.b64 p, [%0], %1;\n@!p bra WL;\n}" ::"r"(bar), "r"(parity) : "memory");
}
__device__ __forceinline__ void mbar_wait_cluster(uint32_t bar, uint32_t parity) {
    uint32_t ok; int n = 0;
    do {
        asm volatile("{\n.reg .pred p;\nmbarrier.try_wait.parity.acquire.cluster.shared::cta.b64 p, [%1], %2;\nselp.u32 %0, 1, 0, p;\n}" : "=r"(ok) : "r"(bar), "r"(parity) : "memory");
        if (++n > SPIN_LIMIT) __trap();
    } while (!ok);
}
__device__ __forceinline__ void warp_arrive(uint32_t bar) {
    __syncwarp();
    asm volatile("{\n.reg .pred p;\nelect.sync _|p, 0xffffffff;\n@p mbarrier.arrive.shared::cta.b64 _, [%0];\n}" ::"r"(bar) : "memory");
}
__device__ __forceinline__ int opaque(int v) { return __shfl_sync(~0u, v, 0); }
__device__ __forceinline__ int fresh_tid() { int v; asm volatile("mov.u32 %0, %%tid.x;" : "=r"(v)); return v; }
__device__ __forceinline__ void bar_sync(int id, int n) { asm volatile("bar.sync %0, %1;" ::"r"(id), "r"(n) : "memory"); }
__device__ __forceinline__ void bar_arrive(int id, int n) { asm volatile("bar.arrive %0, %1;" ::"r"(id), "r"(n) : "memory"); }
__device__ __forceinline__ void fence_async_smem() { asm volatile("fence.proxy.async.shared::cta;" ::: "memory"); }
__device__ __forceinline__ void fence_async_global() { asm volatile("fence.proxy.async.global;" ::: "memory"); }
__device__ __forceinline__ void fence_gpu() { asm volatile("fence.release.gpu;" ::: "memory"); }
__device__ __forceinline__ void tma3(uint32_t dst, const CUtensorMap* m, int c0, int c1, int c2, uint32_t bar) {
    asm volatile("cp.async.bulk.tensor.3d.shared::cluster.global.mbarrier::complete_tx::bytes [%0], [%1, {%3, %4, %5}], [%2];"
                 ::"r"(dst), "l"(m), "r"(bar), "r"(c0), "r"(c1), "r"(c2) : "memory");
}
__device__ __forceinline__ void bulk_load(uint32_t dst, const void* src, uint32_t bytes, uint32_t bar) {
    asm volatile("cp.async.bulk.shared::cluster.global.mbarrier::complete_tx::bytes [%0], [%1], %2, [%3];" ::"r"(dst), "l"(src), "r"(bytes), "r"(bar) : "memory");
}
__device__ __forceinline__ void expect_e(uint32_t bar, uint32_t bytes) {
    asm volatile("{\n.reg .pred p;\nelect.sync _|p, 0xffffffff;\n@p mbarrier.arrive.expect_tx.shared::cta.b64 _, [%0], %1;\n}" ::"r"(bar), "r"(bytes) : "memory");
}
__device__ __forceinline__ void tma3_e(uint32_t dst, const CUtensorMap* m, int c0, int c1, int c2, uint32_t bar) {
    asm volatile("{\n.reg .pred p;\nelect.sync _|p, 0xffffffff;\n@p cp.async.bulk.tensor.3d.shared::cluster.global.mbarrier::complete_tx::bytes [%0], [%1, {%3, %4, %5}], [%2];\n}"
                 ::"r"(dst), "l"(m), "r"(bar), "r"(c0), "r"(c1), "r"(c2) : "memory");
}
__device__ __forceinline__ void bulk_e(uint32_t dst, const void* src, uint32_t bytes, uint32_t bar) {
    asm volatile("{\n.reg .pred p;\nelect.sync _|p, 0xffffffff;\n@p cp.async.bulk.shared::cluster.global.mbarrier::complete_tx::bytes [%0], [%1], %2, [%3];\n}"
                 ::"r"(dst), "l"(src), "r"(bytes), "r"(bar) : "memory");
}
__device__ __forceinline__ void init_e(uint32_t bar, int cnt) {
    asm volatile("{\n.reg .pred p;\nelect.sync _|p, 0xffffffff;\n@p mbarrier.init.shared::cta.b64 [%0], %1;\n}" ::"r"(bar), "r"(cnt) : "memory");
}
__device__ __forceinline__ void l2_prefetch_e(const void* src, uint32_t bytes) {
    asm volatile("{\n.reg .pred p;\nelect.sync _|p, 0xffffffff;\n@p cp.async.bulk.prefetch.L2.global [%0], %1;\n}" ::"l"(src), "r"(bytes) : "memory");
}
__device__ __forceinline__ uint32_t ld_relaxed(const uint32_t* p) { uint32_t v; asm volatile("ld.relaxed.gpu.global.u32 %0, [%1];" : "=r"(v) : "l"(p) : "memory"); return v; }
__device__ __forceinline__ void st_relaxed(uint32_t* p, uint32_t v) { asm volatile("st.relaxed.gpu.global.u32 [%0], %1;" ::"l"(p), "r"(v) : "memory"); }
__device__ __forceinline__ uint4 ld_relaxed4(const uint4* p) { uint4 v; asm volatile("ld.relaxed.gpu.global.v4.u32 {%0,%1,%2,%3}, [%4];" : "=r"(v.x), "=r"(v.y), "=r"(v.z), "=r"(v.w) : "l"(p) : "memory"); return v; }
__device__ __forceinline__ void st_relaxed4(uint4* p, uint4 v) { asm volatile("st.relaxed.gpu.global.v4.u32 [%0], {%1,%2,%3,%4};" ::"l"(p), "r"(v.x), "r"(v.y), "r"(v.z), "r"(v.w) : "memory"); }
__device__ __forceinline__ uint4 ldg_nc4(const void* p) { uint4 v; asm volatile("ld.global.nc.L1::no_allocate.v4.u32 {%0,%1,%2,%3}, [%4];" : "=r"(v.x), "=r"(v.y), "=r"(v.z), "=r"(v.w) : "l"(p)); return v; }
__device__ __forceinline__ uint32_t ldg_nc(const void* p) { uint32_t v; asm volatile("ld.global.nc.u32 %0, [%1];" : "=r"(v) : "l"(p)); return v; }
__device__ __forceinline__ uint32_t ld_acquire(const uint32_t* p) { uint32_t v; asm volatile("ld.acquire.gpu.global.u32 %0, [%1];" : "=r"(v) : "l"(p) : "memory"); return v; }
__device__ __forceinline__ uint4 lds4(uint32_t a) { uint4 v; asm volatile("ld.shared.v4.u32 {%0,%1,%2,%3}, [%4];" : "=r"(v.x), "=r"(v.y), "=r"(v.z), "=r"(v.w) : "r"(a) : "memory"); return v; }
__device__ __forceinline__ float2 lds2f(uint32_t a) { float2 v; asm volatile("ld.shared.v2.f32 {%0,%1}, [%2];" : "=f"(v.x), "=f"(v.y) : "r"(a) : "memory"); return v; }
__device__ __forceinline__ uint32_t lds1(uint32_t a) { uint32_t v; asm volatile("ld.shared.u32 %0, [%1];" : "=r"(v) : "r"(a) : "memory"); return v; }
__device__ __forceinline__ void sts4(uint32_t a, uint4 v) { asm volatile("st.shared.v4.u32 [%0], {%1,%2,%3,%4};" ::"r"(a), "r"(v.x), "r"(v.y), "r"(v.z), "r"(v.w) : "memory"); }
__device__ __forceinline__ void sts2(uint32_t a, uint32_t x, uint32_t y) { asm volatile("st.shared.v2.u32 [%0], {%1,%2};" ::"r"(a), "r"(x), "r"(y) : "memory"); }
__device__ __forceinline__ void sts1(uint32_t a, uint32_t v) { asm volatile("st.shared.u32 [%0], %1;" ::"r"(a), "r"(v) : "memory"); }
__device__ __forceinline__ void stsm4(uint32_t a, uint32_t r0, uint32_t r1, uint32_t r2, uint32_t r3) {
    asm volatile("stmatrix.sync.aligned.m8n8.x4.shared.b16 [%0], {%1,%2,%3,%4};" ::"r"(a), "r"(r0), "r"(r1), "r"(r2), "r"(r3));
}
__device__ __forceinline__ uint32_t pack2(float lo, float hi) { uint32_t r; asm("cvt.rn.bf16x2.f32 %0, %1, %2;" : "=r"(r) : "f"(hi), "f"(lo)); return r; }
__device__ __forceinline__ uint32_t pack2_relu(float lo, float hi) { uint32_t r; asm("cvt.rn.relu.bf16x2.f32 %0, %1, %2;" : "=r"(r) : "f"(hi), "f"(lo)); return r; }
__device__ __forceinline__ uint32_t hfma2(uint32_t a, uint32_t b, uint32_t c) { uint32_t r; asm("fma.rn.bf16x2 %0, %1, %2, %3;" : "=r"(r) : "r"(a), "r"(b), "r"(c)); return r; }
__device__ __forceinline__ uint32_t hmul2(uint32_t a, uint32_t b) { uint32_t r; asm("mul.rn.bf16x2 %0, %1, %2;" : "=r"(r) : "r"(a), "r"(b)); return r; }
__device__ __forceinline__ float bf_lo(uint32_t v) { return __uint_as_float(v << 16); }
__device__ __forceinline__ float bf_hi(uint32_t v) { return __uint_as_float(v & 0xFFFF0000u); }
__device__ __forceinline__ float bf_round(float v) { return bf_lo(pack2(v, 0.f)); }
__device__ __forceinline__ float ex2(float x) { float r; asm("ex2.approx.ftz.f32 %0, %1;" : "=f"(r) : "f"(x)); return r; }
__device__ __forceinline__ void mma16816(float* d, uint32_t a0, uint32_t a1, uint32_t a2, uint32_t a3, uint32_t b0, uint32_t b1) {
    asm("mma.sync.aligned.m16n8k16.row.col.f32.bf16.bf16.f32 {%0,%1,%2,%3}, {%4,%5,%6,%7}, {%8,%9}, {%0,%1,%2,%3};"
        : "+f"(d[0]), "+f"(d[1]), "+f"(d[2]), "+f"(d[3]) : "r"(a0), "r"(a1), "r"(a2), "r"(a3), "r"(b0), "r"(b1));
}
__device__ __forceinline__ void mma16816_first(float* d, uint32_t a0, uint32_t a1, uint32_t a2, uint32_t a3, uint32_t b0, uint32_t b1) {
    asm volatile("mma.sync.aligned.m16n8k16.row.col.f32.bf16.bf16.f32 {%0,%1,%2,%3}, {%4,%5,%6,%7}, {%8,%9}, {%10,%10,%10,%10};"
        : "=f"(d[0]), "=f"(d[1]), "=f"(d[2]), "=f"(d[3]) : "r"(a0), "r"(a1), "r"(a2), "r"(a3), "r"(b0), "r"(b1), "f"(0.f));
}
__device__ __forceinline__ void mma16816_v(float* d, uint32_t a0, uint32_t a1, uint32_t a2, uint32_t a3, uint32_t b0, uint32_t b1) {
    asm volatile("mma.sync.aligned.m16n8k16.row.col.f32.bf16.bf16.f32 {%0,%1,%2,%3}, {%4,%5,%6,%7}, {%8,%9}, {%0,%1,%2,%3};"
        : "+f"(d[0]), "+f"(d[1]), "+f"(d[2]), "+f"(d[3]) : "r"(a0), "r"(a1), "r"(a2), "r"(a3), "r"(b0), "r"(b1));
}
__device__ __forceinline__ void mma1688(float* d, uint32_t a0, uint32_t a1, uint32_t b0) {
    asm("mma.sync.aligned.m16n8k8.row.col.f32.bf16.bf16.f32 {%0,%1,%2,%3}, {%4,%5}, {%6}, {%0,%1,%2,%3};"
        : "+f"(d[0]), "+f"(d[1]), "+f"(d[2]), "+f"(d[3]) : "r"(a0), "r"(a1), "r"(b0));
}
__device__ __forceinline__ void ldsm4(uint32_t a, uint32_t* r) {
    asm volatile("ldmatrix.sync.aligned.m8n8.x4.shared.b16 {%0,%1,%2,%3}, [%4];" : "=r"(r[0]), "=r"(r[1]), "=r"(r[2]), "=r"(r[3]) : "r"(a));
}
__device__ __forceinline__ void ldsm4t(uint32_t a, uint32_t* r) {
    asm volatile("ldmatrix.sync.aligned.m8n8.x4.trans.shared.b16 {%0,%1,%2,%3}, [%4];" : "=r"(r[0]), "=r"(r[1]), "=r"(r[2]), "=r"(r[3]) : "r"(a));
}
__device__ __forceinline__ float rcp(float x) { float r; asm("rcp.approx.ftz.f32 %0, %1;" : "=f"(r) : "f"(x)); return r; }
__device__ __forceinline__ uint2 ld_relaxed2(const void* p) { uint2 v; asm volatile("ld.relaxed.gpu.global.v2.u32 {%0,%1}, [%2];" : "=r"(v.x), "=r"(v.y) : "l"(p) : "memory"); return v; }
__device__ __forceinline__ void st_relaxed2(void* p, uint32_t x, uint32_t y) { asm volatile("st.relaxed.gpu.global.v2.u32 [%0], {%1,%2};" ::"l"(p), "r"(max(x, 1u)), "r"(max(y, 1u)) : "memory"); }
__host__ __device__ constexpr uint64_t dconst(uint32_t lbo, uint32_t sbo, uint32_t swz) {
    return ((uint64_t)(lbo >> 4) << 16) | ((uint64_t)(sbo >> 4) << 32) | ((uint64_t)swz << 62);
}
__device__ __forceinline__ uint32_t mkdesc(uint32_t addr, uint64_t c) { return (uint32_t)c | ((addr & 0x3FFFF) >> 4); }
#define WG_FENCE() asm volatile("wgmma.fence.sync.aligned;" ::: "memory")
#define WG_COMMIT() asm volatile("wgmma.commit_group.sync.aligned;" ::: "memory")
#define WG_WAIT(n) asm volatile("wgmma.wait_group.sync.aligned %0;" ::"n"(n) : "memory")
template <int N> __device__ __forceinline__ void reg_fence(float* d) {
#pragma unroll
    for (int i = 0; i < N; i++) asm volatile("" : "+f"(d[i])::"memory");
}
template <int N> __device__ __forceinline__ void reg_def(float* d) {
#pragma unroll
    for (int i = 0; i < N; i++) asm volatile("" : "=f"(d[i]));
}
template <int N> __device__ __forceinline__ void reg_def(uint32_t* d) {
#pragma unroll
    for (int i = 0; i < N; i++) asm volatile("" : "=r"(d[i]));
}
__device__ __forceinline__ bool is_unset(uint4 v) { return min(min(v.x, v.y), min(v.z, v.w)) == 0u; }
__device__ __forceinline__ uint4 nz4(uint32_t a, uint32_t b, uint32_t c, uint32_t d) { return make_uint4(max(a, 1u), max(b, 1u), max(c, 1u), max(d, 1u)); }
__device__ __forceinline__ void wait_flags(const uint32_t* p, uint32_t target, uint32_t mask) {
    int n = 0;
    while (~__ballot_sync(~0u, (int)(ld_relaxed(p) - target) >= 0) & mask) { if (++n > SPIN_LIMIT) __trap(); }
    asm volatile("fence.acquire.gpu;" ::: "memory");
}
__device__ __forceinline__ float silu_bf(uint32_t cbits) {
    const float c = __uint_as_float(cbits << 16);
    return bf_round(__fdividef(c, 1.f + fminf(ex2(-1.4426950408889634f * c), 1e30f)));
}
__device__ __forceinline__ void gemv_part(uint32_t wmbuf, int npanel, int wp, int lane) {
    const uint32_t wa = wmbuf + wp * 512 + (8 * (lane >> 4) + (lane & 7)) * 32 + ((lane >> 3) & 1) * 16;
    uint2 B[4];
#pragma unroll
    for (int i = 0; i < 4; i++) { const float2 v = lds2f(wmbuf + 28672 + (wp + 8 * i) * 32 + (lane & 3) * 8); B[i] = make_uint2(__float_as_uint(v.x), __float_as_uint(v.y)); }
#pragma unroll 1
    for (int pn = 0; pn < npanel; pn++) {
        float d[4] = {};
        uint32_t A[16];
#pragma unroll
        for (int i = 0; i < 4; i++) ldsm4t(wa + pn * 14336 + (i < 3 || wp < 4 ? i : 0) * 4096, A + 4 * i);
#pragma unroll
        for (int i = 0; i < 4; i++) mma16816(d, A[4 * i], A[4 * i + 1], A[4 * i + 2], A[4 * i + 3], B[i].x, B[i].y);
        if ((lane & 3) == 0) {
            sts1(wmbuf + 29696 + (wp * 32 + pn * 16 + (lane >> 2)) * 4, __float_as_uint(d[0]));
            sts1(wmbuf + 29696 + (wp * 32 + pn * 16 + 8 + (lane >> 2)) * 4, __float_as_uint(d[2]));
        }
    }
}
__device__ __forceinline__ int pass_f(int fs, int ps) { return 224 * fs + ((fs & 1) ? (ps == 0 ? 96 : ps == 1 ? 32 : 0) : (ps == 0 ? 0 : ps == 1 ? 128 : 192)); }
__device__ __forceinline__ constexpr uint32_t slot_off(int l) { return l * 16384; }
__device__ __forceinline__ constexpr int g1_slot(int s) { return s < 3 ? s : s < 6 ? s + 1 : s == 6 ? 3 : s % 7; }
__device__ __forceinline__ void x1_fix(const uint32_t* g, uint32_t sa) {
#pragma unroll 1
    for (int i = 0; i < 8;) {
        const int o = (i >> 1) * 256 + (i & 1) * 32;
        const uint32_t v = ld_relaxed(g + o);
        sts1(sa + 4 * o, v);
        i += __all_sync(~0u, v != 0u);
    }
    __syncwarp();
}
__device__ __forceinline__ void ln_coeffs(float mean, float msq, uint32_t& r2, uint32_t& n2) {
    const float rs = bf_round(rsqrtf(fmaxf(msq - mean * mean, 0.f) + 1e-5f));
    r2 = pack2(rs, rs);
    n2 = pack2(-mean * rs, -mean * rs);
}

#define LOADW bulk_e(dst, g_wd + (size_t)((f >> 5) * 4 + nq) * 1792, 7168, bar);
template <int sec> __device__ __forceinline__ void ring_loader(const Params& p, uint32_t sb_, int r_, int j_, int lane) {
    const uint32_t sb = opaque(sb_);
    const int r = opaque(r_), j = opaque(j_), nq = j >> 1, fs = 4 * (j & 1) + nq;
    const int fa = pass_f(fs, 0), fb = pass_f(fs, 1), fc = pass_f(fs, 2);
#define BAR(i) (sb + M_BAR + 8 * (i))
#define kh (j & 1)
            int sl = 0;
            mbar_wait(BAR(B_PUB + 2), 0);
            wait_flags(g_flag + (8 * r + j) * 128 + 96 + lane, lds1(sb + M_EPOCH) + 1, 0xFFFFu);
            fence_async_global();
#pragma unroll 1
            for (int s = 0; s < 28; s++) {
                const int ps = s < 14 ? 0 : s < 21 ? 1 : 2;
                const uint32_t half = ps < 2 ? 8192 : 4096;
                const int sp = s >= 3 && s < 7 ? (s == 6 ? 3 : s + 1) : sl;
                mbar_wait(BAR(B_EMPTY + sp), (s >= 7 && s < 14) || s >= 21);
                expect_e(BAR(B_FULL + sp), half);
                tma3_e(sb + slot_off(sp) + sec * half, &p.ga + 2 * ps + sec, 0, ps ? 64 * sl : 32 * s, ps == 0 ? fa >> 6 : ps == 1 ? fb >> 6 : fc >> 5, BAR(B_FULL + sp));
                sl = sl == 6 ? 0 : sl + 1;
            }
            if (!sec) PROFH(3);
#pragma unroll 1
            for (int e = 0; e < 4; e++) {
                const uint32_t dst = sb + slot_off(e) + sec * 8192, bar = BAR(B_FULL + e);
                const int f = (e < 2 ? fa + 64 * e : e == 2 ? fb : fc) + 32 * sec;
                mbar_wait(BAR(B_EMPTY + e), 0);
                expect_e(bar, e == 3 && sec ? 0 : 7168);
                if (!(e == 3 && sec)) { LOADW }
            }
            sl = 4;
            int e = 4;
#pragma unroll 1
            for (int grp = 0; grp < 9; grp++) {
                const int ps = grp >= 6 ? 2 : grp >= 3 ? 1 : 0;
                int sidx = grp - 3 * ps;
                if (sec && sidx == 0) { mbar_wait(BAR(B_HRDY + ps), 0); fence_async_global(); }
                sidx += sidx >= nq;
                int f = pass_f(4 * kh + sidx, ps);
#pragma unroll 1
                for (int k = 4 >> ps; k > 0; k--, e++, f += 32) {
                    const uint32_t dst = sb + slot_off(sl), bar = BAR(B_FULL + sl);
                    mbar_wait(BAR(B_EMPTY + sl), e >= 12 && e < 24);
                    if (e < WIN_END && e >= WIN) mbar_wait(BAR(B_FULL + (sl >= WIN ? sl - WIN : sl + 12 - WIN)), e - WIN >= 12);
                    expect_e(bar, sec ? 8192 : 7168);
                    if (!sec) { LOADW }
                    else bulk_e(dst + 8192, p.actb + (size_t)r * RB_WORDS + RB_H2 + f * 64, 8192, bar);
                    sl = sl == 11 ? 0 : sl + 1;
                }
            }
            if (!sec) PROFH(4);
}

__global__ void __cluster_dims__(2, 1, 1) __launch_bounds__(384, 1) fused_block_kernel(const __grid_constant__ Params p) {
    extern __shared__ __align__(1024) unsigned char smem[];
    const uint32_t sb = (uint32_t)__cvta_generic_to_shared(smem);
    const int tid = threadIdx.x, lane = tid & 31, warp = __shfl_sync(~0u, tid >> 5, 0);
    const int m = blockIdx.x >> 1;
    int r, nq;
    {
        int g, i;
        if (m < MAP_S) { g = m < 4 ? 15 : 16; i = m & 3; }
        else if (m < MAP_S + 32) { g = (m - MAP_S) & 7; i = (m - MAP_S) >> 3; }
        else if (m < MAP_S + 60) { i = (m - MAP_S - 32) / 7; g = 8 + (m - MAP_S - 32) - 7 * i; }
        else { g = 16; i = m & 3; }
        r = g; nq = i;
    }
    const int j = opaque(2 * nq + (blockIdx.x & 1)), b = 8 * r + j, fs = 4 * kh + nq;
#define act (p.actb + (size_t)r * RB_WORDS)
    const uint32_t sc = r == 16;
    if (lane == 0 && warp < 9 && warp != 6 && warp != 7) {
        const int i0 = warp == 8 ? 0 : 8 + 8 * warp, cnt = warp == 0 || warp == 8 ? 1 : warp < 3 ? 2 : 8;
#pragma unroll
        for (int k = 0; k < 8; k++) if (i0 + k != B_WMFULL) mbar_init(BAR(i0 + k), cnt);
        asm volatile("fence.mbarrier_init.release.cluster;" ::: "memory");
        fence_async_smem();
    }

    if (warp < 8) {
        const int w = warp >> 2, wi = warp & 3;
#define COORDS const int t = fresh_tid() & 127, lane = t & 31, q = lane & 3, lr = lane >> 2, ra = 64 * w + 16 * wi + lr; \
        const uint32_t lx = (lane >> 4) ^ (lane & 7), mrow = (64 * w + 16 * wi + ((lane >> 3) & 1) * 8 + (lane & 7)) * 128; \
        (void)q; (void)lr; (void)ra; (void)lx; (void)mrow;
        const int sid = 2 * (j & 3) + w;
#define RUN(k) (!sc || sid == (k))
#define WAIT(i, par) mbar_wait_c(BAR(i), (par) | sc)
        constexpr uint64_t DB128 = dconst(4096, 1024, 1);
        bar_arrive(9, 384);
        bar_sync(0, 384);
        asm volatile("barrier.cluster.arrive.relaxed.aligned;" ::: "memory");
        asm volatile("setmaxnreg.inc.sync.aligned.u32 224;");
        PROFC(0);
        uint32_t xr[16];
        {
            COORDS
            uint32_t h[112];
            if (RUN(0)) {
                float ds[4] = {}, da[2][4] = {}, db[2][4] = {};
                const uint32_t ONE2 = 0x3F803F80u;
                if (kh == 0) { WAIT(B_WMFULL, 0); gemv_part(sb + OFF_Y + HALF, 1, warp, lane); warp_arrive(BAR(B_GEMV)); }
#pragma unroll
                for (int kb = 0; kb < 7; kb++) {
                    WAIT(B_XFULL + kb, 0);
#pragma unroll
                    for (int k4 = 0; k4 < 4; k4++) ldsm4(sb + OFF_X + mrow + kb * 16384 + (((2 * k4) ^ lx) << 4), h + 16 * kb + 4 * k4);
#pragma unroll
                    for (int k4 = 0; k4 < 4; k4++) {
                        const uint32_t* f = h + 16 * kb + 4 * k4;
                        mma16816(ds, f[0], f[1], f[2], f[3], ONE2, ONE2);
                        mma1688(da[0], f[0], f[1], f[0]); mma1688(db[0], f[0], f[1], f[1]);
                        mma1688(da[1], f[2], f[3], f[2]); mma1688(db[1], f[2], f[3], f[3]);
                    }
                }
#pragma unroll
                for (int i = 0; i < 4; i++) {
                    const int ch = 7 * j + 2 * i + (lane >> 4);
                    ldsm4(sb + OFF_X + mrow + (ch >> 3) * 16384 + (((ch ^ lane) & 7) << 4), xr + 4 * i);
                }
                warp_arrive(BAR(B_XFREE));
                float qa = (lr & 1) ? da[0][1] + da[1][1] : da[0][0] + da[1][0];
                float qb = (lr & 1) ? db[0][3] + db[1][3] : db[0][2] + db[1][2];
                const int src = (lane & ~3) | (lr >> 1);
                qa = __shfl_sync(~0u, qa, src);
                qb = __shfl_sync(~0u, qb, src);
                uint32_t ra2, na2, rb2, nb2;
                ln_coeffs(ds[0] * (1.f / DM), qa * (1.f / DM), ra2, na2);
                ln_coeffs(ds[2] * (1.f / DM), qb * (1.f / DM), rb2, nb2);
#pragma unroll
                for (int i = 0; i < 112; i += 2) { h[i] = hfma2(h[i], ra2, na2); h[i + 1] = hfma2(h[i + 1], rb2, nb2); }
                if (kh == 1) { WAIT(B_WMFULL, 0); gemv_part(sb + OFF_Y + HALF, 2, warp, lane); warp_arrive(BAR(B_GEMV)); }
            } else { reg_def<112>(h); reg_def<16>(xr); }
            PROFC(1);
            if (RUN(1)) {
                float ak[28], av[28], aq[28];
                uint32_t kp[14], vp[14];
                const uint32_t bk0 = mkdesc(sb + OFF_Y, DB128) + kh, bv0 = mkdesc(sb + OFF_Y + HALF, DB128) + kh, bq0 = mkdesc(sb + OFF_X, DB128) + kh;
                uint32_t* kvg = act + RB_KV + j * 7168 + (8 * w + 2 * wi) * 224 + lane;
                WAIT(B_FULLK, 0);
                WAIT(B_MOD1, 0);
                PROFC(2);
                reg_def<28>(ak);
#pragma unroll
                for (int g4 = 0; g4 < 4; g4++) {
#pragma unroll
                    for (int ks = 7 * g4; ks < 7 * g4 + 7; ks++) {
                        const uint4 st = *(const uint4*)(smem + M_ST + ks * 64 + q * 16);
                        h[4 * ks] = hfma2(h[4 * ks], st.x, st.y); h[4 * ks + 1] = hfma2(h[4 * ks + 1], st.x, st.y);
                        h[4 * ks + 2] = hfma2(h[4 * ks + 2], st.z, st.w); h[4 * ks + 3] = hfma2(h[4 * ks + 3], st.z, st.w);
                    }
                    WG_FENCE();
#pragma unroll
                    for (int ks = 7 * g4; ks < 7 * g4 + 7; ks++) wgmma_rs_56<DB128>(ak, h[4 * ks], h[4 * ks + 1], h[4 * ks + 2], h[4 * ks + 3], bk0 + ks * 128, ks != 0);
                }
                WG_COMMIT();
                PROFC(3);
                WAIT(B_FULLV, 0);
                reg_def<28>(av);
                WG_FENCE();
#pragma unroll
                for (int ks = 0; ks < 8; ks++) wgmma_rs_56<DB128>(av, h[4 * ks], h[4 * ks + 1], h[4 * ks + 2], h[4 * ks + 3], bv0 + ks * 128, ks != 0);
                WG_COMMIT();
                WG_WAIT(1);
                reg_fence<28>(ak);
#pragma unroll
                for (int g = 0; g < 7; g++) {
                    kp[2 * g] = pack2(ak[4 * g], ak[4 * g + 1]); kp[2 * g + 1] = pack2(ak[4 * g + 2], ak[4 * g + 3]);
                    kvg[g * 32] = kp[2 * g]; kvg[224 + g * 32] = kp[2 * g + 1];
                }
                warp_arrive(BAR(B_PUB));
                PROFC(4);
                WG_FENCE();
#pragma unroll
                for (int ks = 8; ks < 28; ks++) wgmma_rs_56<DB128>(av, h[4 * ks], h[4 * ks + 1], h[4 * ks + 2], h[4 * ks + 3], bv0 + ks * 128, 1);
                WG_COMMIT();
                WAIT(B_FULLQ, 0);
                reg_def<28>(aq);
                WG_FENCE();
#pragma unroll
                for (int ks = 0; ks < 8; ks++) wgmma_rs_56<DB128>(aq, h[4 * ks], h[4 * ks + 1], h[4 * ks + 2], h[4 * ks + 3], bq0 + ks * 128, ks != 0);
                WG_COMMIT();
                WG_WAIT(1);
                reg_fence<28>(av);
#pragma unroll
                for (int g = 0; g < 7; g++) {
                    vp[2 * g] = pack2(av[4 * g], av[4 * g + 1]); vp[2 * g + 1] = pack2(av[4 * g + 2], av[4 * g + 3]);
                    kvg[3584 + g * 32] = vp[2 * g]; kvg[3584 + 224 + g * 32] = vp[2 * g + 1];
                }
                warp_arrive(BAR(B_PUB + 1));
                PROFC(5);
                WG_FENCE();
#pragma unroll
                for (int ks = 8; ks < 28; ks++) wgmma_rs_56<DB128>(aq, h[4 * ks], h[4 * ks + 1], h[4 * ks + 2], h[4 * ks + 3], bq0 + ks * 128, 1);
                WG_COMMIT();
                WAIT(B_PUB + 1, 0);
                const uint32_t ko = sb + OFF_Y + Y_KOWN + (8 * w + 2 * wi) * 896 + lane * 4;
                const uint32_t qo = sb + OFF_Y + Y_Q + (8 * w + 2 * wi) * 1024 + lane * 4;
#pragma unroll
                for (int g = 0; g < 7; g++) {
                    sts1(ko + g * 128, kp[2 * g]); sts1(ko + 896 + g * 128, kp[2 * g + 1]);
                    sts1(ko + (Y_VOWN - Y_KOWN) + g * 128, vp[2 * g]); sts1(ko + (Y_VOWN - Y_KOWN) + 896 + g * 128, vp[2 * g + 1]);
                }
                WG_WAIT(0);
                reg_fence<28>(aq);
                __syncwarp();
                if (lane < 3 && w == 1) mbar_arrive(BAR(B_EMPTY + lane));
#pragma unroll
                for (int g = 0; g < 7; g++) {
                    const uint32_t q0 = pack2(aq[4 * g], aq[4 * g + 1]), q1 = pack2(aq[4 * g + 2], aq[4 * g + 3]);
                    if (g == 3) {
                        sts1(qo + 3 * 128, q < 2 ? q0 : 0u); sts1(qo + 1024 + 3 * 128, q < 2 ? q1 : 0u);
                        sts1(qo + 4 * 128, q < 2 ? 0u : q0); sts1(qo + 1024 + 4 * 128, q < 2 ? 0u : q1);
                    } else {
                        const int ch = g < 3 ? g : g + 1;
                        sts1(qo + ch * 128, q0); sts1(qo + 1024 + ch * 128, q1);
                    }
                }
                if (!sc) bar_sync(3, 256);
            }
        }
        PROFC(6);
        WAIT(B_KRFULL, 0);
        PROFC(7);
        if (RUN(2)) {
#pragma unroll 1
            for (int hf = sc; hf < 2; hf++) {
                COORDS
                float s[136];
                float na = 0.f, nb = 0.f;
                const float CS = 0.18898223650461361f * 1.4426950408889634f;
                const int kg0 = 8 * hf + 2 * wi;
                const int pmin = 16 - 8 * r - 4 * hf - wi;
                const float NEG = __int_as_float(0xFF800000);
                {
                    uint32_t F[8];
                    const uint32_t qa = sb + OFF_Y + Y_Q + (kg0 + ((lane >> 3) & 1)) * 1024 + (4 * w + (lane >> 4)) * 128 + (lane & 7) * 16;
                    ldsm4(qa, F); ldsm4(qa + 256, F + 4);
                    uint32_t ka = sb + OFF_Y + Y_K + kg0 * 896 + (3 * w + (lane >> 3)) * 128 + (lane & 7) * 16;
#pragma unroll
                    for (int g = 0; g < 34; g++) {
                        uint32_t B[4];
                        if (g >= 12 && g % 4 == 0) ka += __float_as_uint(s[4 * (g - 12)]) & p.zero;
                        ldsm4(ka + g * 896, B);
                        mma16816_first(s + 4 * g, F[0], F[1], F[2], F[3], B[0], B[1]);
                        mma16816_v(s + 4 * g, F[4], F[5], F[6], F[7], B[2], B[3]);
                    }
                    const bool c0 = 2 * q > lr, c1 = 2 * q + 1 > lr;
                    if (!c0) { s[0] = NEG; s[6] = NEG; }
                    if (!c1) { s[1] = NEG; s[7] = NEG; }
                    s[2] = NEG; s[3] = NEG;
                    if (c0) { s[128] = NEG; s[134] = NEG; }
                    if (c1) { s[129] = NEG; s[135] = NEG; }
                    s[132] = NEG; s[133] = NEG;
                    float ma = NEG, mb = NEG;
#pragma unroll
                    for (int pp = 0; pp < 17; pp++) {
                        const float* e = s + 8 * pp;
                        const float bias = pp < pmin ? NEG : 0.f;
                        ma = fmaxf(ma, fmaxf(fmaxf(e[0], e[1]), fmaxf(e[4], e[5])) + bias);
                        mb = fmaxf(mb, fmaxf(fmaxf(e[2], e[3]), fmaxf(e[6], e[7])) + bias);
                    }
                    ma = fmaxf(ma, __shfl_xor_sync(~0u, ma, 1)); mb = fmaxf(mb, __shfl_xor_sync(~0u, mb, 1));
                    ma = fmaxf(ma, __shfl_xor_sync(~0u, ma, 2)); mb = fmaxf(mb, __shfl_xor_sync(~0u, mb, 2));
                    na = -ma * CS; nb = -mb * CS;
                }
                PROFC(8 + 3 * hf);
                {
                    WAIT(B_VRFULL, 0);
                    float o[16] = {}, rs[4] = {};
                    uint32_t pk[2];
                    const uint32_t va = sb + OFF_Y + Y_VR + (kg0 + ((lane >> 3) & 1)) * 896 + (3 * w + (lane >> 4)) * 128 + (lane & 7) * 16;
#pragma unroll
                    for (int pp = 0; pp < 17; pp++) {
                        uint32_t B[8];
                        const uint32_t v = va + pp * 1792 + (pp == 16 || (pp >= 9 && kg0 + 2 * pp >= 32) ? Y_VOWN - 32 * 896 : 0);
                        ldsm4t(v, B); ldsm4t(v + 256, B + 4);
                        float e[8];
                        const float bias = __uint_as_float((pp < pmin ? 0xFF800000u : 0u) | ((pp < 2 ? B[0] : pk[pp & 1]) & p.zero));
#pragma unroll
                        for (int i = 0; i < 8; i++) e[i] = ex2(fmaf(s[8 * pp + i], CS, ((i & 2) ? nb : na) + bias));
                        const uint32_t p0 = pack2(e[0], e[1]), p1 = pack2(e[2], e[3]), p2 = pack2(e[4], e[5]), p3 = pack2(e[6], e[7]);
                        pk[pp & 1] = p3;
                        mma16816(rs, p0, p1, p2, p3, 0x3F803F80u, 0x3F803F80u);
#pragma unroll
                        for (int g = 0; g < 4; g++) mma16816(o + 4 * g, p0, p1, p2, p3, B[2 * g], B[2 * g + 1]);
                    }
                    PROFC(9 + 3 * hf);
                    const float ia = rcp(rs[0]), ib = rcp(rs[2]);
                    uint32_t* og = act + RB_O + hf * 14336 + (7 * j + 3 * w) * 256 + wi * 64 + lane;
#pragma unroll
                    for (int g = 0; g < 4; g++) {
                        if ((g == 3 - 3 * w) ? ((q >> 1) == w) : true) {
                            og[g * 256] = pack2(o[4 * g] * ia, o[4 * g + 1] * ia);
                            og[g * 256 + 32] = pack2(o[4 * g + 2] * ib, o[4 * g + 3] * ib);
                        }
                    }
                    warp_arrive(BAR(B_PUB + 2 + hf));
                    PROFC(10 + 3 * hf);
                }
            }
        }
        uint32_t x1p[14];
        COORDS
        constexpr uint64_t DT = dconst(1024, 128, 0);
        const int tile = opaque((lds1(sb + M_EPOCH) & 1) * 2 + w);
        if (RUN(4)) {
            float ac[28];
            const uint32_t ad = mkdesc(sb + (w ? OFF_Y + HALF : OFF_X), DT), bd = mkdesc(sb + OFF_X + HALF, DB128) + kh;
            WAIT(B_WOFULL, 0);
            WAIT(B_MOD2, 0);
            WAIT(B_GFULL + w, 0);
            PROFC(28);
            reg_def<28>(ac);
#pragma unroll 1
            for (int u = 0; u < 4; u++) {
                if (u == 2) WAIT(B_XFULL + 2 + w, 1);
                WG_FENCE();
#pragma unroll
                for (int i = 0; i < 7; i++) wgmma_ss_56<DT, DB128>(ac, ad + (7 * u + i) * 128, bd + (7 * u + i) * 128, (u | i) != 0);
            }
            WG_COMMIT();
            WG_WAIT(0);
            reg_fence<28>(ac);
            PROFC(14);
            __syncwarp();
            if (lane < 3) mbar_arrive(BAR(B_EMPTY + 4 + lane));
            if (lane < 3 && w == 0) mbar_arrive(BAR(B_EMPTY + lane));
            float s1a = 0.f, s2a = 0.f, s1b = 0.f, s2b = 0.f;
            uint32_t* xo = act + RB_X1 + tile * 14336 + 7 * j * 256 + wi * 64 + lane;
#pragma unroll
            for (int g = 0; g < 7; g++) {
                const float2 ga = *(const float2*)(smem + M_G + (8 * g + 2 * q) * 4);
                x1p[2 * g] = pack2(fmaf(ga.x, ac[4 * g], bf_lo(xr[2 * g])), fmaf(ga.y, ac[4 * g + 1], bf_hi(xr[2 * g])));
                x1p[2 * g + 1] = pack2(fmaf(ga.x, ac[4 * g + 2], bf_lo(xr[2 * g + 1])), fmaf(ga.y, ac[4 * g + 3], bf_hi(xr[2 * g + 1])));
                st_relaxed(xo + g * 256, max(x1p[2 * g], 1u)); st_relaxed(xo + g * 256 + 32, max(x1p[2 * g + 1], 1u));
                const float u0 = bf_lo(x1p[2 * g]), u1 = bf_hi(x1p[2 * g]), u2 = bf_lo(x1p[2 * g + 1]), u3 = bf_hi(x1p[2 * g + 1]);
                s1a += u0 + u1; s2a += u0 * u0 + u1 * u1; s1b += u2 + u3; s2b += u2 * u2 + u3 * u3;
            }
            float ka = (q & 1) ? s2a : s1a, kb2 = (q & 1) ? s2b : s1b;
            ka += __shfl_xor_sync(~0u, (q & 1) ? s1a : s2a, 1); kb2 += __shfl_xor_sync(~0u, (q & 1) ? s1b : s2b, 1);
            const float kk = ((q & 2) ? kb2 : ka) + __shfl_xor_sync(~0u, (q & 2) ? ka : kb2, 2);
            st_relaxed(act + RB_ST + ((tile * 8 + j) * 64 + 16 * wi + lr + 4 * (q & 2)) * 2 + (q & 1), max(__float_as_uint(kk), 1u));
            __syncwarp();
            if (lane < 2) mbar_arrive(BAR(B_PUB + 4 + w));
        } else reg_def<14>(x1p);
        PROFC(15);
        uint32_t h2a[32], h2b[24];
        {
            const int fa = pass_f(fs, 0), fb = pass_f(fs, 1), fc = pass_f(fs, 2);
            uint32_t* h2g = act + RB_H2 + (8 * w + 2 * wi) * 32 + lane;
            const uint32_t a0 = mkdesc(sb + OFF_Y + w * HALF, DT);
            if (RUN(3)) {
                uint32_t ra2, na2, rb2, nb2;
                {
                    const uint32_t* sg = act + RB_ST + ((tile * 8 + 2 * q) * 64 + 16 * wi + lr) * 2;
                    uint2 u[4];
                    WAIT(B_GFULL + 2 + w, 0);
                    PROFC(16);
#pragma unroll
                    for (int i = 0; i < 4; i++) { const float2 v = lds2f(sb + OFF_X + X_STAT + w * 4096 + ((2 * q + (i >> 1)) * 64 + 16 * wi + lr + 8 * (i & 1)) * 8); u[i] = make_uint2(__float_as_uint(v.x), __float_as_uint(v.y)); }
                    while (__any_sync(~0u, min(min(min(u[0].x, u[0].y), min(u[1].x, u[1].y)), min(min(u[2].x, u[2].y), min(u[3].x, u[3].y))) < 1u - sc)) {
#pragma unroll
                        for (int i = 0; i < 4; i++) u[i] = ld_relaxed2(sg + (i >> 1) * 128 + (i & 1) * 16);
                    }
                    warp_arrive(BAR(B_EMPTY + 3));
                    float v[4] = {__uint_as_float(u[0].x) + __uint_as_float(u[2].x), __uint_as_float(u[0].y) + __uint_as_float(u[2].y),
                                  __uint_as_float(u[1].x) + __uint_as_float(u[3].x), __uint_as_float(u[1].y) + __uint_as_float(u[3].y)};
#pragma unroll
                    for (int i = 0; i < 4; i++) { v[i] += __shfl_xor_sync(~0u, v[i], 1); v[i] += __shfl_xor_sync(~0u, v[i], 2); }
                    ln_coeffs(v[0] * (1.f / DM), v[1] * (1.f / DM), ra2, na2);
                    ln_coeffs(v[2] * (1.f / DM), v[3] * (1.f / DM), rb2, nb2);
                }
                const uint32_t ha = sb + OFF_Y + w * HALF + (lane >> 4) * 1024 + (2 * wi + ((lane >> 3) & 1)) * 128 + (lane & 7) * 16;
                const uint32_t sta = sb + M_ST + q * 16;
                const uint32_t* xg = act + RB_X1 + tile * 14336 + wi * 64 + lane;
                uint32_t x[8];
                const uint32_t xs = sb + OFF_Y + w * HALF + wi * 256 + lane * 4;
                uint4 st[2];
                auto load = [&](int s) {
                    if (s == 4) mbar_wait_c(BAR(B_XFULL + 4 + w), 1);
                    ldsm4(ha + s * 4096, x); ldsm4(ha + s * 4096 + 2048, x + 4);
                    st[0] = lds4(sta + s * 128); st[1] = lds4(sta + s * 128 + 64);
                };
                auto prep = [&](int s, uint32_t* f) {
                    if (__any_sync(~0u, min(min(min(x[0], x[1]), min(x[2], x[3])), min(min(x[4], x[5]), min(x[6], x[7]))) < 1u - sc)) {
                        x1_fix(xg + s * 1024, xs + s * 4096);
                        ldsm4(ha + s * 4096, x); ldsm4(ha + s * 4096 + 2048, x + 4);
                    }
#pragma unroll
                    for (int i = 0; i < 2; i++) {
                        f[4 * i] = hfma2(hfma2(x[4 * i], ra2, na2), st[i].x, st[i].y); f[4 * i + 1] = hfma2(hfma2(x[4 * i + 1], rb2, nb2), st[i].x, st[i].y);
                        f[4 * i + 2] = hfma2(hfma2(x[4 * i + 2], ra2, na2), st[i].z, st[i].w); f[4 * i + 3] = hfma2(hfma2(x[4 * i + 3], rb2, nb2), st[i].z, st[i].w);
                    }
                    if (s < 13) load(s + 1);
                    stsm4(ha + s * 4096, f[0], f[1], f[2], f[3]); stsm4(ha + s * 4096 + 2048, f[4], f[5], f[6], f[7]);
                };
                float ac[128];
                uint32_t fr[3][8];
                const uint32_t bx = mkdesc(sb, DB128);
                reg_def<128>(ac);
                load(0);
                prep(0, fr[0]);
                PROFC(17);
#pragma unroll
                for (int s = 0; s < 14; s++) {
                    const uint32_t* f = fr[s % 3];
                    const uint32_t bd = bx + g1_slot(s) * 1024;
                    WAIT(B_FULL + g1_slot(s), s >= 7);
                    WG_FENCE();
                    wgmma_rs_256<DB128>(ac, f[0], f[1], f[2], f[3], bd, s != 0);
                    wgmma_rs_256<DB128>(ac, f[4], f[5], f[6], f[7], bd + 128, 1);
                    WG_COMMIT();
                    if (s < 13) prep(s + 1, fr[(s + 1) % 3]);
                    if (s > 0) { WG_WAIT(1); warp_arrive(BAR(B_EMPTY + g1_slot(s - 1))); }
                }
                fence_async_smem();
                PROFC(18);
                WG_WAIT(0);
                reg_fence<128>(ac);
                warp_arrive(BAR(B_EMPTY + 6));
#pragma unroll
                for (int g = 0; g < 16; g++) {
                    h2a[2 * g] = hmul2(pack2_relu(ac[4 * g], ac[4 * g + 1]), pack2(ac[64 + 4 * g], ac[64 + 4 * g + 1]));
                    h2a[2 * g + 1] = hmul2(pack2_relu(ac[4 * g + 2], ac[4 * g + 3]), pack2(ac[64 + 4 * g + 2], ac[64 + 4 * g + 3]));
                    h2g[(fa / 8 + g) * 512] = h2a[2 * g]; h2g[(fa / 8 + g) * 512 + 32] = h2a[2 * g + 1];
                }
                warp_arrive(BAR(B_PUB + 6));
                bar_sync(1 + w, 128);
            } else reg_def<32>(h2a);
            PROFC(19);
            if (RUN(5)) {
                float ac[64];
                reg_def<64>(ac);
                const uint32_t bx = mkdesc(sb, dconst(8192, 1024, 1));
#pragma unroll kB
                for (int s = 0; s < 7; s++) {
                    WAIT(B_FULL + s, 0);
                    const uint32_t ad = a0 + s * 512, bd = bx + (slot_off(s) >> 4);
                    WG_FENCE();
#pragma unroll
                    for (int k = 0; k < 4; k++) wgmma_ss_128<DT, DB128>(ac, ad + k * 128, bd + k * 128, (s | k) != 0);
                    WG_COMMIT();
                    if (s > 0) { WG_WAIT(1); warp_arrive(BAR(B_EMPTY + s - 1)); }
                }
                WG_WAIT(0);
                reg_fence<64>(ac);
                warp_arrive(BAR(B_EMPTY + 6));
#pragma unroll
                for (int g = 0; g < 8; g++) {
                    h2b[2 * g] = hmul2(pack2_relu(ac[4 * g], ac[4 * g + 1]), pack2(ac[32 + 4 * g], ac[32 + 4 * g + 1]));
                    h2b[2 * g + 1] = hmul2(pack2_relu(ac[4 * g + 2], ac[4 * g + 3]), pack2(ac[32 + 4 * g + 2], ac[32 + 4 * g + 3]));
                    h2g[(fb / 8 + g) * 512] = h2b[2 * g]; h2g[(fb / 8 + g) * 512 + 32] = h2b[2 * g + 1];
                }
                warp_arrive(BAR(B_PUB + 7));
            } else reg_def<16>(h2b);
            PROFC(27);
            if (RUN(6)) {
                float ac[32];
                reg_def<32>(ac);
                const uint32_t bx = mkdesc(sb, dconst(4096, 512, 2));
#pragma unroll kC
                for (int s = 0; s < 7; s++) {
                    WAIT(B_FULL + s, 1);
                    const uint32_t ad = a0 + s * 512, bd = bx + (slot_off(s) >> 4);
                    WG_FENCE();
#pragma unroll
                    for (int k = 0; k < 4; k++) wgmma_ss_64<DT, dconst(4096, 512, 2)>(ac, ad + k * 128, bd + k * 64, (s | k) != 0);
                    WG_COMMIT();
                    if (s > 0) { WG_WAIT(1); warp_arrive(BAR(B_EMPTY + s - 1)); }
                }
                WG_WAIT(0);
                reg_fence<32>(ac);
                __syncwarp();
                if (lane < 6) mbar_arrive(BAR(B_EMPTY + 6 + lane));
                PROFC(20);
#pragma unroll
                for (int g = 0; g < 4; g++) {
                    h2b[16 + 2 * g] = hmul2(pack2_relu(ac[4 * g], ac[4 * g + 1]), pack2(ac[16 + 4 * g], ac[16 + 4 * g + 1]));
                    h2b[16 + 2 * g + 1] = hmul2(pack2_relu(ac[4 * g + 2], ac[4 * g + 3]), pack2(ac[16 + 4 * g + 2], ac[16 + 4 * g + 3]));
                    h2g[(fc / 8 + g) * 512] = h2b[16 + 2 * g]; h2g[(fc / 8 + g) * 512 + 32] = h2b[16 + 2 * g + 1];
                }
                warp_arrive(BAR(B_PUB + 8));
                asm volatile("barrier.cluster.wait.aligned;" ::: "memory");
                if (lane == 0 && !sc) {
                    uint32_t rb;
                    asm volatile("mapa.shared::cluster.u32 %0, %1, %2;" : "=r"(rb) : "r"(BAR(B_PEER)), "r"(kh ^ 1));
                    asm volatile("mbarrier.arrive.relaxed.cluster.shared::cluster.b64 _, [%0];" ::"r"(rb) : "memory");
                }
            } else reg_def<8>(h2b + 16);
        }
        PROFC(21);
        if (RUN(7)) {
            float ac[56];
            reg_def<56>(ac);
            constexpr uint64_t DAN = dconst(2048, 128, 0);
            constexpr uint64_t DW = dconst(128, 512, 0);
            const uint32_t bx = mkdesc(sb, DW);
#pragma unroll
            for (int e = 0; e < 4; e++) {
                WAIT(B_FULL + e, 0);
                const uint32_t bd = bx + (slot_off(e) >> 4);
                const uint32_t* hh = e < 2 ? h2a + 16 * e : h2b + 16 * (e - 2);
                WG_FENCE();
#pragma unroll
                for (int k = 0; k < (e < 3 ? 4 : 2); k++) wgmma_rs_112<DW>(ac, hh[4 * k], hh[4 * k + 1], hh[4 * k + 2], hh[4 * k + 3], bd + (k >> 1) * 512 + (k & 1) * 16, (e | k) != 0);
                WG_COMMIT();
                if (e > 0) { WG_WAIT(1); warp_arrive(BAR(B_EMPTY + e - 1)); }
            }
            PROFC(22);
            uint32_t ad = mkdesc(sb + 4 * 16384 + 8192 + w * 1024, DAN), bd = bx + 4 * 1024, fb_ = BAR(B_FULL + 4), eb_ = BAR(B_EMPTY + 3), par = sc;
#pragma unroll 1
            for (int e = 4; e < 25; e++) {
                mbar_wait_c(fb_, par);
                WG_FENCE();
                wgmma_ss_112<DAN, DW>(ac, ad, bd, 1);
                wgmma_ss_112<DAN, DW>(ac, ad + 256, bd + 16, 1);
                WG_COMMIT();
                WG_WAIT(1);
                warp_arrive(eb_);
                eb_ = fb_ + 8 * (B_EMPTY - B_FULL);
                ad += 1024; bd += 1024; fb_ += 8;
                if (e == 11 || e == 23) { ad -= 12 * 1024; bd -= 12 * 1024; fb_ -= 96; par = (par ^ 1) | sc; }
            }
            mbar_wait_cluster(BAR(B_PEER), sc);
            WG_WAIT(0);
            reg_fence<56>(ac);
            PROFC(24);
            uint32_t rdst, rbar;
            asm volatile("mapa.shared::cluster.u32 %0, %1, %2;" : "=r"(rdst) : "r"(sb + OFF_Y + (5 + w) * 16384 + t * 16), "r"(kh ^ 1 ^ sc));
            asm volatile("mapa.shared::cluster.u32 %0, %1, %2;" : "=r"(rbar) : "r"(BAR(B_XCH + w)), "r"(kh ^ 1 ^ sc));
#define ACG(g, i) ac[4 * (g) + (i)]
#pragma unroll
            for (int g = 0; g < 7; g++) {
                const float v0 = kh ? ACG(g, 0) : ACG(g + 7, 0), v1 = kh ? ACG(g, 1) : ACG(g + 7, 1);
                const float v2 = kh ? ACG(g, 2) : ACG(g + 7, 2), v3 = kh ? ACG(g, 3) : ACG(g + 7, 3);
                if (!sc) asm volatile("st.async.shared::cluster.mbarrier::complete_tx::bytes.v4.f32 [%0], {%1,%2,%3,%4}, [%5];"
                             ::"r"(rdst + g * 2048), "f"(v0), "f"(v1), "f"(v2), "f"(v3), "r"(rbar) : "memory");
            }
            mbar_wait_cluster(BAR(B_XCH + w), sc);
            PROFC(25);
            bf16* og = (sc ? (bf16*)act : p.out + (size_t)128 * r * DM) + (size_t)ra * DM + 56 * j + 2 * q;
#pragma unroll
            for (int g = 0; g < 7; g++) {
                const uint4 rv = *(const uint4*)(smem + OFF_Y + (5 + w) * 16384 + t * 16 + g * 2048);
                const float2 gb = *(const float2*)(smem + M_G + 224 + (8 * g + 2 * q) * 4);
                const float v0 = (kh ? ACG(g + 7, 0) : ACG(g, 0)) + __uint_as_float(rv.x), v1 = (kh ? ACG(g + 7, 1) : ACG(g, 1)) + __uint_as_float(rv.y);
                const float v2 = (kh ? ACG(g + 7, 2) : ACG(g, 2)) + __uint_as_float(rv.z), v3 = (kh ? ACG(g + 7, 3) : ACG(g, 3)) + __uint_as_float(rv.w);
                *(uint32_t*)(og + 8 * g) = pack2(fmaf(gb.x, v0, bf_lo(x1p[2 * g])), fmaf(gb.y, v1, bf_hi(x1p[2 * g])));
                *(uint32_t*)(og + 8 * DM + 8 * g) = pack2(fmaf(gb.x, v2, bf_lo(x1p[2 * g + 1])), fmaf(gb.y, v3, bf_hi(x1p[2 * g + 1])));
            }
        }
        PROFC(26);
        bar_sync(1 + w, 128);
        if (wi == 0) warp_arrive(BAR(B_DONE));
    } else {
        const int lane = fresh_tid() & 31;
        const bool early = kh == 0, gemv = r < 14;
        const int mcol = early ? 16 * (4 * r + nq) : 2 * DM + 32 * (4 * r + nq);
        const uint32_t wmbuf = sb + OFF_Y + HALF;
        asm volatile("setmaxnreg.dec.sync.aligned.u32 56;");
        if (warp == 9) {
#pragma unroll
            for (int i = 56; i < 64; i++) init_e(BAR(i), 1);
            fence_async_smem();
        }
        if (warp == 8) { init_e(BAR(B_WMFULL), 2); fence_async_smem(); }
        bar_arrive(0, 384);
        asm volatile("barrier.cluster.arrive.relaxed.aligned;" ::: "memory");
        uint32_t target = 0;
        if (warp == 8) {
            if (!sc) {
                expect_e(BAR(B_WMFULL), gemv ? 28672 >> early : 0);
                if (early && gemv) { tma3_e(wmbuf, &p.wm, mcol, 0, 0, BAR(B_WMFULL)); tma3_e(wmbuf + 7168, &p.wm, mcol, 224, 0, BAR(B_WMFULL)); }
#pragma unroll 1
                for (int kb = 0; kb < 7; kb++) {
                    expect_e(BAR(B_XFULL + kb), 16384);
                    tma3_e(sb + OFF_X + kb * 16384, &p.xm, 64 * kb, 128 * r, 0, BAR(B_XFULL + kb));
                }
            }
#pragma unroll 1
            for (int mt = 0; mt < 4; mt++) {
                if (mt == 1) {
                    if (!early && gemv) {
#pragma unroll 1
                        for (int k = 0; k < 4; k++) tma3_e(wmbuf + k * 7168, &p.wm, mcol + (k >> 1) * 16, (k & 1) * 224, 0, BAR(B_WMFULL));
                    }
                    bar_sync(9, 384);
                    if (sc) return;
                    mbar_wait(BAR(B_MOD1), 0);
                    mbar_wait(BAR(B_WMFREE), 0);
                }
                if (mt == 2) mbar_wait(BAR(B_XFREE), 0);
                if (mt == 3) mbar_wait(BAR(B_VRFULL), 0);
                const uint32_t bar = BAR(mt == 3 ? B_WOFULL : B_FULLK + mt), dst = sb + (mt < 2 ? OFF_Y : OFF_X) + (mt & 1) * HALF;
                const int c0 = (mt < 2 ? DM + DM * mt : 0) + 56 * j - 8 * kh;
                if (!sc) {
                    expect_e(bar, HALF);
                    tma3_e(dst, mt == 3 ? &p.wo : &p.qkv, c0, 0, 0, bar);
                    tma3_e(dst + HALF / 2, mt == 3 ? &p.wo : &p.qkv, c0, 224, 0, bar);
                }
            }
            expect_e(BAR(B_XCH), 14336);
            expect_e(BAR(B_XCH + 1), 14336);
        } else {
            if (warp == 10 && !sc) {
                l2_prefetch_e((const char*)p.wqkv + (size_t)b * 9408, 9408);
                if (lane == 0) sts1(sb + M_EPOCH, atomicAdd(&g_ticket, 1u) / NCTA);
            }
            if (warp == 11) {
#pragma unroll
                for (int i = 0; i < 8; i++) {
                    const int wd = lane + 32 * i;
                    const uint32_t cb = i < 7 ? __ldg((const uint32_t*)p.c + wd) : 0u;
                    sts1(wmbuf + 28672 + (wd >> 3) * 32 + (wd & 3) * 8 + (wd & 4), pack2(silu_bf(cb & 0xFFFFu), silu_bf(cb >> 16)));
                }
            }
            bar_sync(9, 384);
            if (sc) return;
            target = lds1(sb + M_EPOCH) + 1;
            const uint32_t tag = target & 0xFFFFu;
            if (warp == 11) {
                warp_arrive(BAR(B_WMFULL));
                mbar_wait(BAR(B_GEMV), 0);
                float sum = 0.f;
#pragma unroll
                for (int i = 0; i < 8; i++) sum += *(const float*)(smem + OFF_Y + HALF + 29696 + (i * 32 + (early ? lane & 15 : lane)) * 4);
                const uint32_t word = (pack2(sum, 0.f) << 16) | tag;
                if (gemv) {
                    uint32_t* mg = g_mod + mcol + (early ? (lane & 15) + (lane >> 4) * 4 * 6 * DM : lane);
#pragma unroll
                    for (int i = 0; i < 8; i++) if (i < 4 || !early) st_relaxed(mg + i * 6 * DM, word);
                }
                warp_arrive(BAR(B_WMFREE));
            }
            const uint4* modp = (const uint4*)g_mod + (r & 7) * (6 * DM / 4);
            const bool p2 = warp == 11;
            mbar_wait(BAR(p2 ? B_PUB : B_XFULL + 4), 0);
#pragma unroll 1
            for (int it = p2 ? 0 : warp - 9; it < (p2 ? 2 : warp - 8); it++) {
                const int i0 = lane + 32 * it, imax = p2 ? 251 : 223;
                uint4 v[4];
#pragma unroll 1
                for (int n = 0;; n++) {
                    uint32_t bad = 0;
#pragma unroll
                    for (int k = 0; k < 4; k++) {
                        const int i = min(i0 + 64 * k, imax);
                        v[k] = ld_relaxed4(modp + (i < 224 ? (p2 ? 336 : 0) + i : (i < 238 ? 14 * j + i : 14 * j + i + 322)));
                        bad |= (v[k].x ^ tag) | (v[k].y ^ tag) | (v[k].z ^ tag) | (v[k].w ^ tag);
                    }
                    if (!__any_sync(~0u, bad & 0xFFFFu)) break;
                    if (n > SPIN_LIMIT) __trap();
                }
#pragma unroll
                for (int k = 0; k < 4; k++) {
                    const int i = min(i0 + 64 * k, imax);
                    if (i < 224) {
                        const int isc = i >= 112, c4 = i - 112 * isc;
                        const float one = isc ? 1.f : 0.f;
                        const uint32_t a = sb + M_ST + (c4 >> 2) * 64 + (c4 & 1) * 32 + (c4 & 2) * 4 + (isc ? 0 : 4);
                        sts1(a, pack2(bf_hi(v[k].x) + one, bf_hi(v[k].y) + one));
                        sts1(a + 16, pack2(bf_hi(v[k].z) + one, bf_hi(v[k].w) + one));
                    } else {
                        sts4(sb + M_G + (i - 224) * 16, make_uint4(v[k].x & 0xFFFF0000u, v[k].y & 0xFFFF0000u, v[k].z & 0xFFFF0000u, v[k].w & 0xFFFF0000u));
                    }
                }
                warp_arrive(BAR(p2 ? B_MOD2 : B_MOD1));
            }
            if (warp == 9) {
#pragma unroll 1
                for (int kv = 0; kv < 2; kv++) {
                    mbar_wait(BAR(B_PUB + kv), 0);
                    wait_flags(g_flag + b * 128 + lane, target, (r >= 2 ? 6u : r == 1 ? 2u : 0u) << (8 * kv));
                    fence_async_global();
                    const uint32_t dst = sb + OFF_Y + (kv ? Y_VR : Y_K);
                    expect_e(BAR(B_KRFULL + kv), r >= 2 ? 28672 : r == 1 ? 14336 : 0);
                    if (r >= 2) bulk_e(dst, act - 2 * RB_WORDS + RB_KV + j * 7168 + kv * 3584, 14336, BAR(B_KRFULL + kv));
                    if (r >= 1) bulk_e(dst + 14336, act - RB_WORDS + RB_KV + j * 7168 + kv * 3584, 14336, BAR(B_KRFULL + kv));
                }
            } else if (warp == 11) {
                mbar_wait(BAR(B_VRFULL), 0);
                l2_prefetch_e((const char*)p.wg + (size_t)b * 12544, 12544);
                l2_prefetch_e((const char*)p.wu + (size_t)b * 12544, 12544);
#pragma unroll 1
                for (int k = 0; k < (r < 12 ? 2 : 1); k++) {
                    const int u = 28 * kh + r + 16 * k;
                    expect_e(BAR(B_XFULL + k), 7168);
                    tma3_e(sb + OFF_Y + 102400, &p.dn, 0, 32 * u, 14 * nq, BAR(B_XFULL + k));
                    mbar_wait(BAR(B_XFULL + k), 1);
                    asm volatile("{\n.reg .pred p;\nelect.sync _|p, 0xffffffff;\n@p cp.async.bulk.global.shared::cta.bulk_group [%0], [%1], 7168;\n"
                                 "cp.async.bulk.commit_group;\ncp.async.bulk.wait_group 0;\n}" ::"l"(g_wd + (size_t)(u * 4 + nq) * 1792), "r"(sb + OFF_Y + 102400) : "memory");
                    __syncwarp();
                }
                warp_arrive(BAR(B_WMFREE));
                fence_gpu();
                if (lane < 16) st_relaxed(g_flag + (8 * lane + j) * 128 + 96 + r, target);
            }
        }
        if (warp == 8 || warp == 11) {
            const int sec = warp == 11;
            if (sec) ring_loader<1>(p, sb, r, j, lane); else ring_loader<0>(p, sb, r, j, lane);
            mbar_wait(BAR(B_DONE), 0);
        } else if (warp == 9) {
#pragma unroll
            for (int ev = 0; ev < 4; ev++) { expect_e(BAR(B_GFULL + ev), ev < 2 ? HALF / 2 : 16384 + 4096); expect_e(BAR(B_XFULL + 2 + ev), ev < 2 ? HALF / 2 : HALF - 16384); }
            mbar_wait(BAR(B_PUB + 2), 0);
            const uint32_t* fp = g_flag + b * 128 + 32 + lane;
            const int par = (target - 1) & 1;
#pragma unroll 1
            for (int n = 0, ev = 0; ev < 4; n++) {
                if (ev == 1) { mbar_wait(BAR(B_WMFREE), 1); mbar_wait(BAR(B_PUB + 3), 0); }
                uint32_t ok = __ballot_sync(~0u, (int)(ld_relaxed(fp) - target) >= 0) >> (8 * ev);
                while ((ok & 0xFFu) == 0xFFu) {
                    asm volatile("fence.acquire.gpu;" ::: "memory");
                    fence_async_global();
                    const int tile = (ev & 1) + (ev >> 1) * par * 2;
                    const uint32_t dst = sb + (ev == 0 ? OFF_X : OFF_Y + (ev & 1) * HALF), first = ev < 2 ? HALF / 2 : 16384;
                    const char* src = (const char*)(act + RB_O + ((ev >> 1) * 2 + tile) * 14336);
                    if (ev >= 2) bulk_e(sb + OFF_X + X_STAT + (ev & 1) * 4096, act + RB_ST + tile * 1024, 4096, BAR(B_GFULL + ev));
                    bulk_e(dst, src, first, BAR(B_GFULL + ev));
                    bulk_e(dst + first, src + first, HALF - first, BAR(B_XFULL + 2 + ev));
                    if (ev) PROFH(4 + ev);
                    ev++; ok >>= 8;
                }
                if (n > SPIN_LIMIT) __trap();
            }
            mbar_wait(BAR(B_XFULL + 5), 1);
#pragma unroll 1
            for (int hf = 0; hf < 2; hf++) {
                const int tile = (par ^ 1) * 2 + hf;
                uint4* xz = (uint4*)(act + RB_X1 + tile * 14336 + j * 1792) + lane;
#pragma unroll
                for (int i = 0; i < 14; i++) xz[i * 32] = make_uint4(0, 0, 0, 0);
                ((uint4*)(act + RB_ST + (tile * 8 + j) * 128))[lane] = make_uint4(0, 0, 0, 0);
            }
#pragma unroll 1
            for (int ps = 0; ps < 3; ps++) {
                mbar_wait(BAR(B_PUB + 6 + ps), 0);
                wait_flags(g_flag + b * 128 + 64 + lane, target, (0x55u << kh) << (8 * ps));
                warp_arrive(BAR(B_HRDY + ps));
                PROFH(9 + ps);
            }
        } else {
#pragma unroll 1
            for (int k = 0; k < 9; k++) {
                uint32_t* fp = k < 2 ? g_flag + (b + 8 * lane) * 128 + k * 8 + lane : g_flag + (8 * r + lane) * 128 + 16 + k * 8 + j;
                mbar_wait(BAR(B_PUB + k), 0);
                if (k != 4 && k != 5) fence_gpu();
                if (k < 2 ? (lane == 1 || lane == 2) : lane < 8) st_relaxed(fp, target);
                if (k >= 3 && k <= 5) PROFH(k - 3);
            }
        }
    }
}

#undef act
typedef CUresult (*EncodeFn)(CUtensorMap*, CUtensorMapDataType, cuuint32_t, void*, const cuuint64_t*, const cuuint64_t*, const cuuint32_t*,
                             const cuuint32_t*, CUtensorMapInterleave, CUtensorMapSwizzle, CUtensorMapL2promotion, CUtensorMapFloatOOBfill);

static void make_map(EncodeFn fn, CUtensorMap* m, const void* ptr, uint64_t d0, uint64_t d1, uint64_t d2, uint64_t s1, uint64_t s2,
                     uint32_t b0, uint32_t b1, uint32_t b2, CUtensorMapSwizzle sw) {
    cuuint64_t dims[3] = {d0, d1, d2}, strides[2] = {s1, s2};
    cuuint32_t box[3] = {b0, b1, b2}, es[3] = {1, 1, 1};
    CUresult rc = fn(m, CU_TENSOR_MAP_DATA_TYPE_BFLOAT16, 3, (void*)ptr, dims, strides, box, es, CU_TENSOR_MAP_INTERLEAVE_NONE, sw,
                     CU_TENSOR_MAP_L2_PROMOTION_L2_128B, CU_TENSOR_MAP_FLOAT_OOB_FILL_NONE);
    (void)rc;
}

extern "C" void kernel_launch(void* const* d_in, const int* in_sizes, int n_in, void* d_out, int out_size) {
    (void)in_sizes; (void)n_in; (void)out_size;
    static EncodeFn fn = nullptr;
    static uint32_t* act_base = nullptr;
    if (!fn) {
        cudaDriverEntryPointQueryResult st;
        cudaGetDriverEntryPoint("cuTensorMapEncodeTiled", (void**)&fn, cudaEnableDefault, &st);
        void* a = nullptr;
        cudaGetSymbolAddress(&a, g_act);
        act_base = (uint32_t*)(((uintptr_t)a + 0xFFFFF) & ~(uintptr_t)0xFFFFF);
        cudaFuncSetAttribute(fused_block_kernel, cudaFuncAttributeMaxDynamicSharedMemorySize, SMEM_BYTES);
    }
    Params p;
    p.x = (const bf16*)d_in[0];
    const bf16* wqkv = (const bf16*)d_in[1];
    p.wqkv = wqkv;
    p.wop = (const bf16*)d_in[2];
    p.wg = (const bf16*)d_in[4];
    p.wu = (const bf16*)d_in[5];
    p.wd = (const bf16*)d_in[6];
    p.c = (const bf16*)d_in[7];
    p.wmod = (const bf16*)d_in[8];
    p.out = (bf16*)d_out;
    p.zero = 0;
    p.actb = act_base;
    make_map(fn, &p.wm, p.wmod, 2688, 448, 1, 5376, 5376 * 448, 16, 224, 1, CU_TENSOR_MAP_SWIZZLE_NONE);
    make_map(fn, &p.xm, p.x, 448, 2048, 1, 896, 896 * 2048, 64, 128, 1, CU_TENSOR_MAP_SWIZZLE_128B);
    make_map(fn, &p.qkv, wqkv, 1344, 448, 1, 2688, 2688 * 448, 64, 224, 1, CU_TENSOR_MAP_SWIZZLE_128B);
    make_map(fn, &p.wo, p.wop, 448, 448, 1, 896, 896 * 448, 64, 224, 1, CU_TENSOR_MAP_SWIZZLE_128B);
    make_map(fn, &p.ga, p.wg, 64, 448, 28, 3584, 128, 64, 32, 2, CU_TENSOR_MAP_SWIZZLE_128B);
    make_map(fn, &p.ua, p.wu, 64, 448, 28, 3584, 128, 64, 32, 2, CU_TENSOR_MAP_SWIZZLE_128B);
    make_map(fn, &p.gb, p.wg, 64, 448, 28, 3584, 128, 64, 64, 1, CU_TENSOR_MAP_SWIZZLE_128B);
    make_map(fn, &p.ub, p.wu, 64, 448, 28, 3584, 128, 64, 64, 1, CU_TENSOR_MAP_SWIZZLE_128B);
    make_map(fn, &p.gc, p.wg, 32, 448, 56, 3584, 64, 32, 64, 1, CU_TENSOR_MAP_SWIZZLE_64B);
    make_map(fn, &p.uc, p.wu, 32, 448, 56, 3584, 64, 32, 64, 1, CU_TENSOR_MAP_SWIZZLE_64B);
    make_map(fn, &p.dn, p.wd, 8, 1792, 56, 896, 16, 8, 32, 14, CU_TENSOR_MAP_SWIZZLE_NONE);
    fused_block_kernel<<<GRID, 384, SMEM_BYTES>>>(p);
}
```

```cpp
#include <cuda_runtime.h>
#include <cuda_bf16.h>
#include <cuda.h>
#include <stdint.h>

typedef __nv_bfloat16 bf16;

template<uint64_t CB> __device__ __forceinline__ void wgmma_rs_56(float* d, uint32_t a0, uint32_t a1, uint32_t a2, uint32_t a3, uint32_t db, int sd) {
  asm volatile("{\n.reg .pred p;\n.reg .b64 b;\nsetp.ne.b32 p, %33, 0;\nmov.b64 b, {%32, %34};\n"
    "wgmma.mma_async.sync.aligned.m64n56k16.f32.bf16.bf16 {%0,%1,%2,%3,%4,%5,%6,%7,%8,%9,%10,%11,%12,%13,%14,%15,%16,%17,%18,%19,%20,%21,%22,%23,%24,%25,%26,%27}, {%28,%29,%30,%31}, b, p, 1, 1, 1;\n}\n"
    : "+f"(d[0]),"+f"(d[1]),"+f"(d[2]),"+f"(d[3]),"+f"(d[4]),"+f"(d[5]),"+f"(d[6]),"+f"(d[7]),"+f"(d[8]),"+f"(d[9]),"+f"(d[10]),"+f"(d[11]),"+f"(d[12]),"+f"(d[13]),"+f"(d[14]),"+f"(d[15]),"+f"(d[16]),"+f"(d[17]),"+f"(d[18]),"+f"(d[19]),"+f"(d[20]),"+f"(d[21]),"+f"(d[22]),"+f"(d[23]),"+f"(d[24]),"+f"(d[25]),"+f"(d[26]),"+f"(d[27])
    : "r"(a0), "r"(a1), "r"(a2), "r"(a3), "r"(db), "r"(sd), "n"((uint32_t)(CB >> 32)));
}
template<uint64_t CA, uint64_t CB> __device__ __forceinline__ void wgmma_ss_56(float* d, uint32_t da, uint32_t db, int sd) {
  asm volatile("{\n.reg .pred p;\n.reg .b64 a, b;\nsetp.ne.b32 p, %30, 0;\nmov.b64 a, {%28, %31};\nmov.b64 b, {%29, %32};\n"
    "wgmma.mma_async.sync.aligned.m64n56k16.f32.bf16.bf16 {%0,%1,%2,%3,%4,%5,%6,%7,%8,%9,%10,%11,%12,%13,%14,%15,%16,%17,%18,%19,%20,%21,%22,%23,%24,%25,%26,%27}, a, b, p, 1, 1, 0, 1;\n}\n"
    : "+f"(d[0]),"+f"(d[1]),"+f"(d[2]),"+f"(d[3]),"+f"(d[4]),"+f"(d[5]),"+f"(d[6]),"+f"(d[7]),"+f"(d[8]),"+f"(d[9]),"+f"(d[10]),"+f"(d[11]),"+f"(d[12]),"+f"(d[13]),"+f"(d[14]),"+f"(d[15]),"+f"(d[16]),"+f"(d[17]),"+f"(d[18]),"+f"(d[19]),"+f"(d[20]),"+f"(d[21]),"+f"(d[22]),"+f"(d[23]),"+f"(d[24]),"+f"(d[25]),"+f"(d[26]),"+f"(d[27])
    : "r"(da), "r"(db), "r"(sd), "n"((uint32_t)(CA >> 32)), "n"((uint32_t)(CB >> 32)));
}
template<uint64_t CB> __device__ __forceinline__ void wgmma_rs_256(float* d, uint32_t a0, uint32_t a1, uint32_t a2, uint32_t a3, uint32_t db, int sd) {
  asm volatile("{\n.reg .pred p;\n.reg .b64 b;\nsetp.ne.b32 p, %133, 0;\nmov.b64 b, {%132, %134};\n"
    "wgmma.mma_async.sync.aligned.m64n256k16.f32.bf16.bf16 {%0,%1,%2,%3,%4,%5,%6,%7,%8,%9,%10,%11,%12,%13,%14,%15,%16,%17,%18,%19,%20,%21,%22,%23,%24,%25,%26,%27,%28,%29,%30,%31,%32,%33,%34,%35,%36,%37,%38,%39,%40,%41,%42,%43,%44,%45,%46,%47,%48,%49,%50,%51,%52,%53,%54,%55,%56,%57,%58,%59,%60,%61,%62,%63,%64,%65,%66,%67,%68,%69,%70,%71,%72,%73,%74,%75,%76,%77,%78,%79,%80,%81,%82,%83,%84,%85,%86,%87,%88,%89,%90,%91,%92,%93,%94,%95,%96,%97,%98,%99,%100,%101,%102,%103,%104,%105,%106,%107,%108,%109,%110,%111,%112,%113,%114,%115,%116,%117,%118,%119,%120,%121,%122,%123,%124,%125,%126,%127}, {%128,%129,%130,%131}, b, p, 1, 1, 1;\n}\n"
    : "+f"(d[0]),"+f"(d[1]),"+f"(d[2]),"+f"(d[3]),"+f"(d[4]),"+f"(d[5]),"+f"(d[6]),"+f"(d[7]),"+f"(d[8]),"+f"(d[9]),"+f"(d[10]),"+f"(d[11]),"+f"(d[12]),"+f"(d[13]),"+f"(d[14]),"+f"(d[15]),"+f"(d[16]),"+f"(d[17]),"+f"(d[18]),"+f"(d[19]),"+f"(d[20]),"+f"(d[21]),"+f"(d[22]),"+f"(d[23]),"+f"(d[24]),"+f"(d[25]),"+f"(d[26]),"+f"(d[27]),"+f"(d[28]),"+f"(d[29]),"+f"(d[30]),"+f"(d[31]),"+f"(d[32]),"+f"(d[33]),"+f"(d[34]),"+f"(d[35]),"+f"(d[36]),"+f"(d[37]),"+f"(d[38]),"+f"(d[39]),"+f"(d[40]),"+f"(d[41]),"+f"(d[42]),"+f"(d[43]),"+f"(d[44]),"+f"(d[45]),"+f"(d[46]),"+f"(d[47]),"+f"(d[48]),"+f"(d[49]),"+f"(d[50]),"+f"(d[51]),"+f"(d[52]),"+f"(d[53]),"+f"(d[54]),"+f"(d[55]),"+f"(d[56]),"+f"(d[57]),"+f"(d[58]),"+f"(d[59]),"+f"(d[60]),"+f"(d[61]),"+f"(d[62]),"+f"(d[63]),"+f"(d[64]),"+f"(d[65]),"+f"(d[66]),"+f"(d[67]),"+f"(d[68]),"+f"(d[69]),"+f"(d[70]),"+f"(d[71]),"+f"(d[72]),"+f"(d[73]),"+f"(d[74]),"+f"(d[75]),"+f"(d[76]),"+f"(d[77]),"+f"(d[78]),"+f"(d[79]),"+f"(d[80]),"+f"(d[81]),"+f"(d[82]),"+f"(d[83]),"+f"(d[84]),"+f"(d[85]),"+f"(d[86]),"+f"(d[87]),"+f"(d[88]),"+f"(d[89]),"+f"(d[90]),"+f"(d[91]),"+f"(d[92]),"+f"(d[93]),"+f"(d[94]),"+f"(d[95]),"+f"(d[96]),"+f"(d[97]),"+f"(d[98]),"+f"(d[99]),"+f"(d[100]),"+f"(d[101]),"+f"(d[102]),"+f"(d[103]),"+f"(d[104]),"+f"(d[105]),"+f"(d[106]),"+f"(d[107]),"+f"(d[108]),"+f"(d[109]),"+f"(d[110]),"+f"(d[111]),"+f"(d[112]),"+f"(d[113]),"+f"(d[114]),"+f"(d[115]),"+f"(d[116]),"+f"(d[117]),"+f"(d[118]),"+f"(d[119]),"+f"(d[120]),"+f"(d[121]),"+f"(d[122]),"+f"(d[123]),"+f"(d[124]),"+f"(d[125]),"+f"(d[126]),"+f"(d[127])
    : "r"(a0), "r"(a1), "r"(a2), "r"(a3), "r"(db), "r"(sd), "n"((uint32_t)(CB >> 32)));
}
template<uint64_t CA, uint64_t CB> __device__ __forceinline__ void wgmma_ss_128(float* d, uint32_t da, uint32_t db, int sd) {
  asm volatile("{\n.reg .pred p;\n.reg .b64 a, b;\nsetp.ne.b32 p, %66, 0;\nmov.b64 a, {%64, %67};\nmov.b64 b, {%65, %68};\n"
    "wgmma.mma_async.sync.aligned.m64n128k16.f32.bf16.bf16 {%0,%1,%2,%3,%4,%5,%6,%7,%8,%9,%10,%11,%12,%13,%14,%15,%16,%17,%18,%19,%20,%21,%22,%23,%24,%25,%26,%27,%28,%29,%30,%31,%32,%33,%34,%35,%36,%37,%38,%39,%40,%41,%42,%43,%44,%45,%46,%47,%48,%49,%50,%51,%52,%53,%54,%55,%56,%57,%58,%59,%60,%61,%62,%63}, a, b, p, 1, 1, 0, 1;\n}\n"
    : "+f"(d[0]),"+f"(d[1]),"+f"(d[2]),"+f"(d[3]),"+f"(d[4]),"+f"(d[5]),"+f"(d[6]),"+f"(d[7]),"+f"(d[8]),"+f"(d[9]),"+f"(d[10]),"+f"(d[11]),"+f"(d[12]),"+f"(d[13]),"+f"(d[14]),"+f"(d[15]),"+f"(d[16]),"+f"(d[17]),"+f"(d[18]),"+f"(d[19]),"+f"(d[20]),"+f"(d[21]),"+f"(d[22]),"+f"(d[23]),"+f"(d[24]),"+f"(d[25]),"+f"(d[26]),"+f"(d[27]),"+f"(d[28]),"+f"(d[29]),"+f"(d[30]),"+f"(d[31]),"+f"(d[32]),"+f"(d[33]),"+f"(d[34]),"+f"(d[35]),"+f"(d[36]),"+f"(d[37]),"+f"(d[38]),"+f"(d[39]),"+f"(d[40]),"+f"(d[41]),"+f"(d[42]),"+f"(d[43]),"+f"(d[44]),"+f"(d[45]),"+f"(d[46]),"+f"(d[47]),"+f"(d[48]),"+f"(d[49]),"+f"(d[50]),"+f"(d[51]),"+f"(d[52]),"+f"(d[53]),"+f"(d[54]),"+f"(d[55]),"+f"(d[56]),"+f"(d[57]),"+f"(d[58]),"+f"(d[59]),"+f"(d[60]),"+f"(d[61]),"+f"(d[62]),"+f"(d[63])
    : "r"(da), "r"(db), "r"(sd), "n"((uint32_t)(CA >> 32)), "n"((uint32_t)(CB >> 32)));
}
template<uint64_t CA, uint64_t CB> __device__ __forceinline__ void wgmma_ss_64(float* d, uint32_t da, uint32_t db, int sd) {
  asm volatile("{\n.reg .pred p;\n.reg .b64 a, b;\nsetp.ne.b32 p, %34, 0;\nmov.b64 a, {%32, %35};\nmov.b64 b, {%33, %36};\n"
    "wgmma.mma_async.sync.aligned.m64n64k16.f32.bf16.bf16 {%0,%1,%2,%3,%4,%5,%6,%7,%8,%9,%10,%11,%12,%13,%14,%15,%16,%17,%18,%19,%20,%21,%22,%23,%24,%25,%26,%27,%28,%29,%30,%31}, a, b, p, 1, 1, 0, 1;\n}\n"
    : "+f"(d[0]),"+f"(d[1]),"+f"(d[2]),"+f"(d[3]),"+f"(d[4]),"+f"(d[5]),"+f"(d[6]),"+f"(d[7]),"+f"(d[8]),"+f"(d[9]),"+f"(d[10]),"+f"(d[11]),"+f"(d[12]),"+f"(d[13]),"+f"(d[14]),"+f"(d[15]),"+f"(d[16]),"+f"(d[17]),"+f"(d[18]),"+f"(d[19]),"+f"(d[20]),"+f"(d[21]),"+f"(d[22]),"+f"(d[23]),"+f"(d[24]),"+f"(d[25]),"+f"(d[26]),"+f"(d[27]),"+f"(d[28]),"+f"(d[29]),"+f"(d[30]),"+f"(d[31])
    : "r"(da), "r"(db), "r"(sd), "n"((uint32_t)(CA >> 32)), "n"((uint32_t)(CB >> 32)));
}
template<uint64_t CA, uint64_t CB> __device__ __forceinline__ void wgmma_ss_112(float* d, uint32_t da, uint32_t db, int sd) {
  asm volatile("{\n.reg .pred p;\n.reg .b64 a, b;\nsetp.ne.b32 p, %58, 0;\nmov.b64 a, {%56, %59};\nmov.b64 b, {%57, %60};\n"
    "wgmma.mma_async.sync.aligned.m64n112k16.f32.bf16.bf16 {%0,%1,%2,%3,%4,%5,%6,%7,%8,%9,%10,%11,%12,%13,%14,%15,%16,%17,%18,%19,%20,%21,%22,%23,%24,%25,%26,%27,%28,%29,%30,%31,%32,%33,%34,%35,%36,%37,%38,%39,%40,%41,%42,%43,%44,%45,%46,%47,%48,%49,%50,%51,%52,%53,%54,%55}, a, b, p, 1, 1, 0, 1;\n}\n"
    : "+f"(d[0]),"+f"(d[1]),"+f"(d[2]),"+f"(d[3]),"+f"(d[4]),"+f"(d[5]),"+f"(d[6]),"+f"(d[7]),"+f"(d[8]),"+f"(d[9]),"+f"(d[10]),"+f"(d[11]),"+f"(d[12]),"+f"(d[13]),"+f"(d[14]),"+f"(d[15]),"+f"(d[16]),"+f"(d[17]),"+f"(d[18]),"+f"(d[19]),"+f"(d[20]),"+f"(d[21]),"+f"(d[22]),"+f"(d[23]),"+f"(d[24]),"+f"(d[25]),"+f"(d[26]),"+f"(d[27]),"+f"(d[28]),"+f"(d[29]),"+f"(d[30]),"+f"(d[31]),"+f"(d[32]),"+f"(d[33]),"+f"(d[34]),"+f"(d[35]),"+f"(d[36]),"+f"(d[37]),"+f"(d[38]),"+f"(d[39]),"+f"(d[40]),"+f"(d[41]),"+f"(d[42]),"+f"(d[43]),"+f"(d[44]),"+f"(d[45]),"+f"(d[46]),"+f"(d[47]),"+f"(d[48]),"+f"(d[49]),"+f"(d[50]),"+f"(d[51]),"+f"(d[52]),"+f"(d[53]),"+f"(d[54]),"+f"(d[55])
    : "r"(da), "r"(db), "r"(sd), "n"((uint32_t)(CA >> 32)), "n"((uint32_t)(CB >> 32)));
}
template<uint64_t CB> __device__ __forceinline__ void wgmma_rs_112(float* d, uint32_t a0, uint32_t a1, uint32_t a2, uint32_t a3, uint32_t db, int sd) {
  asm volatile("{\n.reg .pred p;\n.reg .b64 b;\nsetp.ne.b32 p, %61, 0;\nmov.b64 b, {%60, %62};\n"
    "wgmma.mma_async.sync.aligned.m64n112k16.f32.bf16.bf16 {%0,%1,%2,%3,%4,%5,%6,%7,%8,%9,%10,%11,%12,%13,%14,%15,%16,%17,%18,%19,%20,%21,%22,%23,%24,%25,%26,%27,%28,%29,%30,%31,%32,%33,%34,%35,%36,%37,%38,%39,%40,%41,%42,%43,%44,%45,%46,%47,%48,%49,%50,%51,%52,%53,%54,%55}, {%56,%57,%58,%59}, b, p, 1, 1, 1;\n}\n"
    : "+f"(d[0]),"+f"(d[1]),"+f"(d[2]),"+f"(d[3]),"+f"(d[4]),"+f"(d[5]),"+f"(d[6]),"+f"(d[7]),"+f"(d[8]),"+f"(d[9]),"+f"(d[10]),"+f"(d[11]),"+f"(d[12]),"+f"(d[13]),"+f"(d[14]),"+f"(d[15]),"+f"(d[16]),"+f"(d[17]),"+f"(d[18]),"+f"(d[19]),"+f"(d[20]),"+f"(d[21]),"+f"(d[22]),"+f"(d[23]),"+f"(d[24]),"+f"(d[25]),"+f"(d[26]),"+f"(d[27]),"+f"(d[28]),"+f"(d[29]),"+f"(d[30]),"+f"(d[31]),"+f"(d[32]),"+f"(d[33]),"+f"(d[34]),"+f"(d[35]),"+f"(d[36]),"+f"(d[37]),"+f"(d[38]),"+f"(d[39]),"+f"(d[40]),"+f"(d[41]),"+f"(d[42]),"+f"(d[43]),"+f"(d[44]),"+f"(d[45]),"+f"(d[46]),"+f"(d[47]),"+f"(d[48]),"+f"(d[49]),"+f"(d[50]),"+f"(d[51]),"+f"(d[52]),"+f"(d[53]),"+f"(d[54]),"+f"(d[55])
    : "r"(a0), "r"(a1), "r"(a2), "r"(a3), "r"(db), "r"(sd), "n"((uint32_t)(CB >> 32)));
}

constexpr int DM = 448;
constexpr int NCTA = 128;
#define MAPPING 1
#define GRID 132
#define PINGPONG 0
#define WIN 6
#define WIN_END 25
#define UNR_B 1
#define UNR_C 1
constexpr int kB = UNR_B, kC = UNR_C;
#define MAP_S 4
constexpr int SPIN_LIMIT = 1 << 22;

constexpr uint32_t OFF_X = 0, OFF_Y = 114688, OFF_MISC = 229376, SMEM_BYTES = 232448;
constexpr uint32_t Y_VR = 0, Y_K = 28672, Y_KOWN = 57344, Y_VOWN = 71680, Y_Q = 86016;
constexpr uint32_t HALF = 57344;
constexpr uint32_t X_STAT = 49152;
constexpr uint32_t M_BAR = OFF_MISC;
constexpr uint32_t M_ST = OFF_MISC + 512;
constexpr uint32_t M_G = OFF_MISC + 2304;
constexpr uint32_t M_EPOCH = OFF_MISC + 3040;
enum { B_XFULL = 0, B_FULLK = 7, B_FULLV = 8, B_FULLQ, B_KRFULL, B_VRFULL, B_WOFULL, B_XCH, B_MOD1 = 15, B_FULL = 16, B_WMFULL = 30,
       B_EMPTY = 32, B_XFREE = B_EMPTY + 12, B_GEMV, B_PEER,
       B_PUB = 47,
       B_WMFREE = 56, B_HRDY, B_GFULL = B_HRDY + 3, B_DONE = 31, B_DUMMY = B_GEMV };

__device__ uint32_t g_ticket;
__device__ __align__(128) uint32_t g_mod[8 * 6 * DM];
__device__ __align__(128) uint32_t g_flag[144 * 128];
constexpr int RB_WORDS = 262144, RB_KV = 0, RB_O = 57344, RB_X1 = 86016, RB_H2 = 143360, RB_ST = 258048;
__device__ __align__(128) uint32_t g_act[18 * RB_WORDS];
__device__ __align__(128) uint32_t g_wd[56 * 4 * 1792];
#define PROFH(id)
#define PROFH1(id)
#define PROFC(id)

struct alignas(64) Params {
    CUtensorMap wm, xm, qkv, wo, ga, ua, gb, ub, gc, uc, dn;
    const bf16 *x, *c, *wqkv, *wmod, *wg, *wu, *wd, *wop;
    bf16* out;
    uint32_t* actb;
    uint32_t zero;
};

__device__ __forceinline__ void mbar_init(uint32_t bar, int cnt) { asm volatile("mbarrier.init.shared::cta.b64 [%0], %1;" ::"r"(bar), "r"(cnt) : "memory"); }
__device__ __forceinline__ void mbar_expect_tx(uint32_t bar, uint32_t bytes) { asm volatile("mbarrier.arrive.expect_tx.shared::cta.b64 _, [%0], %1;" ::"r"(bar), "r"(bytes) : "memory"); }
__device__ __forceinline__ void mbar_arrive(uint32_t bar) { asm volatile("mbarrier.arrive.shared::cta.b64 _, [%0];" ::"r"(bar) : "memory"); }
__device__ __forceinline__ void mbar_wait(uint32_t bar, uint32_t parity) {
    uint32_t ok; int n = 0;
    do {
        asm volatile("{\n.reg .pred p;\nmbarrier.try_wait.parity.shared::cta.b64 p, [%1], %2;\nselp.u32 %0, 1, 0, p;\n}" : "=r"(ok) : "r"(bar), "r"(parity) : "memory");
        if (++n > SPIN_LIMIT) __trap();
    } while (!ok);
}
__device__ __forceinline__ void mbar_wait_c(uint32_t bar, uint32_t parity) {
    asm volatile("{\n.reg .pred p;\nWL:\nmbarrier.try_wait.parity.shared::cta.b64 p, [%0], %1;\n@!p bra WL;\n}" ::"r"(bar), "r"(parity) : "memory");
}
__device__ __forceinline__ void mbar_wait_cluster(uint32_t bar, uint32_t parity) {
    uint32_t ok; int n = 0;
    do {
        asm volatile("{\n.reg .pred p;\nmbarrier.try_wait.parity.acquire.cluster.shared::cta.b64 p, [%1], %2;\nselp.u32 %0, 1, 0, p;\n}" : "=r"(ok) : "r"(bar), "r"(parity) : "memory");
        if (++n > SPIN_LIMIT) __trap();
    } while (!ok);
}
__device__ __forceinline__ void warp_arrive(uint32_t bar) {
    __syncwarp();
    asm volatile("{\n.reg .pred p;\nelect.sync _|p, 0xffffffff;\n@p mbarrier.arrive.shared::cta.b64 _, [%0];\n}" ::"r"(bar) : "memory");
}
__device__ __forceinline__ int opaque(int v) { return __shfl_sync(~0u, v, 0); }
__device__ __forceinline__ int fresh_tid() { int v; asm volatile("mov.u32 %0, %%tid.x;" : "=r"(v)); return v; }
__device__ __forceinline__ void bar_sync(int id, int n) { asm volatile("bar.sync %0, %1;" ::"r"(id), "r"(n) : "memory"); }
__device__ __forceinline__ void bar_arrive(int id, int n) { asm volatile("bar.arrive %0, %1;" ::"r"(id), "r"(n) : "memory"); }
__device__ __forceinline__ void fence_async_smem() { asm volatile("fence.proxy.async.shared::cta;" ::: "memory"); }
__device__ __forceinline__ void fence_async_global() { asm volatile("fence.proxy.async.global;" ::: "memory"); }
__device__ __forceinline__ void fence_gpu() { asm volatile("fence.release.gpu;" ::: "memory"); }
__device__ __forceinline__ void tma3(uint32_t dst, const CUtensorMap* m, int c0, int c1, int c2, uint32_t bar) {
    asm volatile("cp.async.bulk.tensor.3d.shared::cluster.global.mbarrier::complete_tx::bytes [%0], [%1, {%3, %4, %5}], [%2];"
                 ::"r"(dst), "l"(m), "r"(bar), "r"(c0), "r"(c1), "r"(c2) : "memory");
}
__device__ __forceinline__ void bulk_load(uint32_t dst, const void* src, uint32_t bytes, uint32_t bar) {
    asm volatile("cp.async.bulk.shared::cluster.global.mbarrier::complete_tx::bytes [%0], [%1], %2, [%3];" ::"r"(dst), "l"(src), "r"(bytes), "r"(bar) : "memory");
}
__device__ __forceinline__ void expect_e(uint32_t bar, uint32_t bytes) {
    asm volatile("{\n.reg .pred p;\nelect.sync _|p, 0xffffffff;\n@p mbarrier.arrive.expect_tx.shared::cta.b64 _, [%0], %1;\n}" ::"r"(bar), "r"(bytes) : "memory");
}
__device__ __forceinline__ void tma3_e(uint32_t dst, const CUtensorMap* m, int c0, int c1, int c2, uint32_t bar) {
    asm volatile("{\n.reg .pred p;\nelect.sync _|p, 0xffffffff;\n@p cp.async.bulk.tensor.3d.shared::cluster.global.mbarrier::complete_tx::bytes [%0], [%1, {%3, %4, %5}], [%2];\n}"
                 ::"r"(dst), "l"(m), "r"(bar), "r"(c0), "r"(c1), "r"(c2) : "memory");
}
__device__ __forceinline__ void bulk_e(uint32_t dst, const void* src, uint32_t bytes, uint32_t bar) {
    asm volatile("{\n.reg .pred p;\nelect.sync _|p, 0xffffffff;\n@p cp.async.bulk.shared::cluster.global.mbarrier::complete_tx::bytes [%0], [%1], %2, [%3];\n}"
                 ::"r"(dst), "l"(src), "r"(bytes), "r"(bar) : "memory");
}
__device__ __forceinline__ void init_e(uint32_t bar, int cnt) {
    asm volatile("{\n.reg .pred p;\nelect.sync _|p, 0xffffffff;\n@p mbarrier.init.shared::cta.b64 [%0], %1;\n}" ::"r"(bar), "r"(cnt) : "memory");
}
__device__ __forceinline__ void l2_prefetch_e(const void* src, uint32_t bytes) {
    asm volatile("{\n.reg .pred p;\nelect.sync _|p, 0xffffffff;\n@p cp.async.bulk.prefetch.L2.global [%0], %1;\n}" ::"l"(src), "r"(bytes) : "memory");
}
__device__ __forceinline__ uint32_t ld_relaxed(const uint32_t* p) { uint32_t v; asm volatile("ld.relaxed.gpu.global.u32 %0, [%1];" : "=r"(v) : "l"(p) : "memory"); return v; }
__device__ __forceinline__ void st_relaxed(uint32_t* p, uint32_t v) { asm volatile("st.relaxed.gpu.global.u32 [%0], %1;" ::"l"(p), "r"(v) : "memory"); }
__device__ __forceinline__ uint4 ld_relaxed4(const uint4* p) { uint4 v; asm volatile("ld.relaxed.gpu.global.v4.u32 {%0,%1,%2,%3}, [%4];" : "=r"(v.x), "=r"(v.y), "=r"(v.z), "=r"(v.w) : "l"(p) : "memory"); return v; }
__device__ __forceinline__ void st_relaxed4(uint4* p, uint4 v) { asm volatile("st.relaxed.gpu.global.v4.u32 [%0], {%1,%2,%3,%4};" ::"l"(p), "r"(v.x), "r"(v.y), "r"(v.z), "r"(v.w) : "memory"); }
__device__ __forceinline__ uint4 ldg_nc4(const void* p) { uint4 v; asm volatile("ld.global.nc.L1::no_allocate.v4.u32 {%0,%1,%2,%3}, [%4];" : "=r"(v.x), "=r"(v.y), "=r"(v.z), "=r"(v.w) : "l"(p)); return v; }
__device__ __forceinline__ uint32_t ldg_nc(const void* p) { uint32_t v; asm volatile("ld.global.nc.u32 %0, [%1];" : "=r"(v) : "l"(p)); return v; }
__device__ __forceinline__ uint32_t ld_acquire(const uint32_t* p) { uint32_t v; asm volatile("ld.acquire.gpu.global.u32 %0, [%1];" : "=r"(v) : "l"(p) : "memory"); return v; }
__device__ __forceinline__ uint4 lds4(uint32_t a) { uint4 v; asm volatile("ld.shared.v4.u32 {%0,%1,%2,%3}, [%4];" : "=r"(v.x), "=r"(v.y), "=r"(v.z), "=r"(v.w) : "r"(a) : "memory"); return v; }
__device__ __forceinline__ float2 lds2f(uint32_t a) { float2 v; asm volatile("ld.shared.v2.f32 {%0,%1}, [%2];" : "=f"(v.x), "=f"(v.y) : "r"(a) : "memory"); return v; }
__device__ __forceinline__ uint32_t lds1(uint32_t a) { uint32_t v; asm volatile("ld.shared.u32 %0, [%1];" : "=r"(v) : "r"(a) : "memory"); return v; }
__device__ __forceinline__ void sts4(uint32_t a, uint4 v) { asm volatile("st.shared.v4.u32 [%0], {%1,%2,%3,%4};" ::"r"(a), "r"(v.x), "r"(v.y), "r"(v.z), "r"(v.w) : "memory"); }
__device__ __forceinline__ void sts2(uint32_t a, uint32_t x, uint32_t y) { asm volatile("st.shared.v2.u32 [%0], {%1,%2};" ::"r"(a), "r"(x), "r"(y) : "memory"); }
__device__ __forceinline__ void sts1(uint32_t a, uint32_t v) { asm volatile("st.shared.u32 [%0], %1;" ::"r"(a), "r"(v) : "memory"); }
__device__ __forceinline__ void stsm4(uint32_t a, uint32_t r0, uint32_t r1, uint32_t r2, uint32_t r3) {
    asm volatile("stmatrix.sync.aligned.m8n8.x4.shared.b16 [%0], {%1,%2,%3,%4};" ::"r"(a), "r"(r0), "r"(r1), "r"(r2), "r"(r3));
}
__device__ __forceinline__ uint32_t pack2(float lo, float hi) { uint32_t r; asm("cvt.rn.bf16x2.f32 %0, %1, %2;" : "=r"(r) : "f"(hi), "f"(lo)); return r; }
__device__ __forceinline__ uint32_t pack2_relu(float lo, float hi) { uint32_t r; asm("cvt.rn.relu.bf16x2.f32 %0, %1, %2;" : "=r"(r) : "f"(hi), "f"(lo)); return r; }
__device__ __forceinline__ uint32_t hfma2(uint32_t a, uint32_t b, uint32_t c) { uint32_t r; asm("fma.rn.bf16x2 %0, %1, %2, %3;" : "=r"(r) : "r"(a), "r"(b), "r"(c)); return r; }
__device__ __forceinline__ uint32_t hmul2(uint32_t a, uint32_t b) { uint32_t r; asm("mul.rn.bf16x2 %0, %1, %2;" : "=r"(r) : "r"(a), "r"(b)); return r; }
__device__ __forceinline__ float bf_lo(uint32_t v) { return __uint_as_float(v << 16); }
__device__ __forceinline__ float bf_hi(uint32_t v) { return __uint_as_float(v & 0xFFFF0000u); }
__device__ __forceinline__ float bf_round(float v) { return bf_lo(pack2(v, 0.f)); }
__device__ __forceinline__ float ex2(float x) { float r; asm("ex2.approx.ftz.f32 %0, %1;" : "=f"(r) : "f"(x)); return r; }
__device__ __forceinline__ void mma16816(float* d, uint32_t a0, uint32_t a1, uint32_t a2, uint32_t a3, uint32_t b0, uint32_t b1) {
    asm("mma.sync.aligned.m16n8k16.row.col.f32.bf16.bf16.f32 {%0,%1,%2,%3}, {%4,%5,%6,%7}, {%8,%9}, {%0,%1,%2,%3};"
        : "+f"(d[0]), "+f"(d[1]), "+f"(d[2]), "+f"(d[3]) : "r"(a0), "r"(a1), "r"(a2), "r"(a3), "r"(b0), "r"(b1));
}
__device__ __forceinline__ void mma16816_first(float* d, uint32_t a0, uint32_t a1, uint32_t a2, uint32_t a3, uint32_t b0, uint32_t b1) {
    asm volatile("mma.sync.aligned.m16n8k16.row.col.f32.bf16.bf16.f32 {%0,%1,%2,%3}, {%4,%5,%6,%7}, {%8,%9}, {%10,%10,%10,%10};"
        : "=f"(d[0]), "=f"(d[1]), "=f"(d[2]), "=f"(d[3]) : "r"(a0), "r"(a1), "r"(a2), "r"(a3), "r"(b0), "r"(b1), "f"(0.f));
}
__device__ __forceinline__ void mma16816_v(float* d, uint32_t a0, uint32_t a1, uint32_t a2, uint32_t a3, uint32_t b0, uint32_t b1) {
    asm volatile("mma.sync.aligned.m16n8k16.row.col.f32.bf16.bf16.f32 {%0,%1,%2,%3}, {%4,%5,%6,%7}, {%8,%9}, {%0,%1,%2,%3};"
        : "+f"(d[0]), "+f"(d[1]), "+f"(d[2]), "+f"(d[3]) : "r"(a0), "r"(a1), "r"(a2), "r"(a3), "r"(b0), "r"(b1));
}
__device__ __forceinline__ void mma1688(float* d, uint32_t a0, uint32_t a1, uint32_t b0) {
    asm("mma.sync.aligned.m16n8k8.row.col.f32.bf16.bf16.f32 {%0,%1,%2,%3}, {%4,%5}, {%6}, {%0,%1,%2,%3};"
        : "+f"(d[0]), "+f"(d[1]), "+f"(d[2]), "+f"(d[3]) : "r"(a0), "r"(a1), "r"(b0));
}
__device__ __forceinline__ void ldsm4(uint32_t a, uint32_t* r) {
    asm volatile("ldmatrix.sync.aligned.m8n8.x4.shared.b16 {%0,%1,%2,%3}, [%4];" : "=r"(r[0]), "=r"(r[1]), "=r"(r[2]), "=r"(r[3]) : "r"(a));
}
__device__ __forceinline__ void ldsm4t(uint32_t a, uint32_t* r) {
    asm volatile("ldmatrix.sync.aligned.m8n8.x4.trans.shared.b16 {%0,%1,%2,%3}, [%4];" : "=r"(r[0]), "=r"(r[1]), "=r"(r[2]), "=r"(r[3]) : "r"(a));
}
__device__ __forceinline__ float rcp(float x) { float r; asm("rcp.approx.ftz.f32 %0, %1;" : "=f"(r) : "f"(x)); return r; }
__device__ __forceinline__ uint2 ld_relaxed2(const void* p) { uint2 v; asm volatile("ld.relaxed.gpu.global.v2.u32 {%0,%1}, [%2];" : "=r"(v.x), "=r"(v.y) : "l"(p) : "memory"); return v; }
__device__ __forceinline__ void st_relaxed2(void* p, uint32_t x, uint32_t y) { asm volatile("st.relaxed.gpu.global.v2.u32 [%0], {%1,%2};" ::"l"(p), "r"(max(x, 1u)), "r"(max(y, 1u)) : "memory"); }
__host__ __device__ constexpr uint64_t dconst(uint32_t lbo, uint32_t sbo, uint32_t swz) {
    return ((uint64_t)(lbo >> 4) << 16) | ((uint64_t)(sbo >> 4) << 32) | ((uint64_t)swz << 62);
}
__device__ __forceinline__ uint32_t mkdesc(uint32_t addr, uint64_t c) { return (uint32_t)c | ((addr & 0x3FFFF) >> 4); }
#define WG_FENCE() asm volatile("wgmma.fence.sync.aligned;" ::: "memory")
#define WG_COMMIT() asm volatile("wgmma.commit_group.sync.aligned;" ::: "memory")
#define WG_WAIT(n) asm volatile("wgmma.wait_group.sync.aligned %0;" ::"n"(n) : "memory")
template <int N> __device__ __forceinline__ void reg_fence(float* d) {
#pragma unroll
    for (int i = 0; i < N; i++) asm volatile("" : "+f"(d[i])::"memory");
}
template <int N> __device__ __forceinline__ void reg_def(float* d) {
#pragma unroll
    for (int i = 0; i < N; i++) asm volatile("" : "=f"(d[i]));
}
template <int N> __device__ __forceinline__ void reg_def(uint32_t* d) {
#pragma unroll
    for (int i = 0; i < N; i++) asm volatile("" : "=r"(d[i]));
}
__device__ __forceinline__ bool is_unset(uint4 v) { return min(min(v.x, v.y), min(v.z, v.w)) == 0u; }
__device__ __forceinline__ uint4 nz4(uint32_t a, uint32_t b, uint32_t c, uint32_t d) { return make_uint4(max(a, 1u), max(b, 1u), max(c, 1u), max(d, 1u)); }
__device__ __forceinline__ void wait_flags(const uint32_t* p, uint32_t target, uint32_t mask) {
    int n = 0;
    while (~__ballot_sync(~0u, (int)(ld_relaxed(p) - target) >= 0) & mask) { if (++n > SPIN_LIMIT) __trap(); }
    asm volatile("fence.acquire.gpu;" ::: "memory");
}
__device__ __forceinline__ float silu_bf(uint32_t cbits) {
    const float c = __uint_as_float(cbits << 16);
    return bf_round(__fdividef(c, 1.f + fminf(ex2(-1.4426950408889634f * c), 1e30f)));
}
__device__ __forceinline__ void gemv_part(uint32_t wmbuf, int npanel, int wp, int lane) {
    const uint32_t wa = wmbuf + wp * 512 + (8 * (lane >> 4) + (lane & 7)) * 32 + ((lane >> 3) & 1) * 16;
    uint2 B[4];
#pragma unroll
    for (int i = 0; i < 4; i++) { const float2 v = lds2f(wmbuf + 28672 + (wp + 8 * i) * 32 + (lane & 3) * 8); B[i] = make_uint2(__float_as_uint(v.x), __float_as_uint(v.y)); }
#pragma unroll 1
    for (int pn = 0; pn < npanel; pn++) {
        float d[4] = {};
        uint32_t A[16];
#pragma unroll
        for (int i = 0; i < 4; i++) ldsm4t(wa + pn * 14336 + (i < 3 || wp < 4 ? i : 0) * 4096, A + 4 * i);
#pragma unroll
        for (int i = 0; i < 4; i++) mma16816(d, A[4 * i], A[4 * i + 1], A[4 * i + 2], A[4 * i + 3], B[i].x, B[i].y);
        if ((lane & 3) == 0) {
            sts1(wmbuf + 29696 + (wp * 32 + pn * 16 + (lane >> 2)) * 4, __float_as_uint(d[0]));
            sts1(wmbuf + 29696 + (wp * 32 + pn * 16 + 8 + (lane >> 2)) * 4, __float_as_uint(d[2]));
        }
    }
}
__device__ __forceinline__ const uint4* mod_src(int i, int r, int j, bool p2) {
    i = min(i, p2 ? 251 : 223);
    return (const uint4*)g_mod + (r & 7) * (6 * DM / 4) + (i < 224 ? (p2 ? 336 : 0) + i : (i < 238 ? 14 * j + i : 14 * j + i + 322));
}
__device__ __forceinline__ void mod_store(uint32_t sb, uint4 v, const uint4* src, int i, uint32_t sc) {
    const uint32_t tag = lds1(sb + M_EPOCH) + 1;
    while (__any_sync(~0u, (((v.x ^ tag) | (v.y ^ tag) | (v.z ^ tag) | (v.w ^ tag)) & 0xFFFFu) != 0u) && !sc) v = ld_relaxed4(src);
    if (i < 224) {
        const int isc = i >= 112, c4 = i - 112 * isc;
        const uint32_t a = sb + M_ST + (c4 >> 2) * 64 + (c4 & 1) * 32 + (c4 & 2) * 4 + (isc ? 0 : 4);
        sts1(a, __byte_perm(v.x, v.y, 0x7632));
        sts1(a + 16, __byte_perm(v.z, v.w, 0x7632));
    } else if (i < 252) {
        sts4(sb + M_G + (i - 224) * 16, make_uint4(v.x & 0xFFFF0000u, v.y & 0xFFFF0000u, v.z & 0xFFFF0000u, v.w & 0xFFFF0000u));
    }
}
__device__ __forceinline__ int pass_f(int fs, int ps) { return 224 * fs + ((fs & 1) ? (ps == 0 ? 96 : ps == 1 ? 32 : 0) : (ps == 0 ? 0 : ps == 1 ? 128 : 192)); }
__device__ __forceinline__ constexpr uint32_t slot_off(int l) { return l * 16384; }
__device__ __forceinline__ constexpr int g1_slot(int s) { return s < 3 ? s : s < 6 ? s + 1 : s == 6 ? 3 : s % 7; }
__device__ __forceinline__ void x1_check(const uint32_t* g, uint32_t sa, int n, uint32_t sc) {
#pragma unroll 1
    for (int i = 0; i < n; i += 8) {
        uint32_t mn = ~0u;
#pragma unroll
        for (int k = 0; k < 4; k++) { const uint4 v = lds4(sa + (i + 2 * k) * 1024); mn = min(min(mn, v.x), min(min(v.y, v.z), v.w)); }
        if (__any_sync(~0u, mn < 1u - sc)) {
#pragma unroll 1
            for (int k = 0; k < 4;) {
                const uint4 v = ld_relaxed4((const uint4*)(g + (i + 2 * k) * 256));
                sts4(sa + (i + 2 * k) * 1024, v);
                k += __all_sync(~0u, min(min(v.x, v.y), min(v.z, v.w)) != 0u);
            }
        }
    }
    __syncwarp();
}
__device__ __forceinline__ void ln_coeffs(float mean, float msq, uint32_t& r2, uint32_t& n2) {
    const float rs = bf_round(rsqrtf(fmaxf(msq - mean * mean, 0.f) + 1e-5f));
    r2 = pack2(rs, rs);
    n2 = pack2(-mean * rs, -mean * rs);
}

#define LOADW bulk_e(dst, g_wd + (size_t)((f >> 5) * 4 + nq) * 1792, 7168, bar);
template <int sec> __device__ __forceinline__ void ring_loader(const Params& p, uint32_t sb_, int r_, int j_, int lane) {
    const uint32_t sb = opaque(sb_);
    const int r = opaque(r_), j = opaque(j_), nq = j >> 1, fs = 4 * (j & 1) + nq;
    const int fa = pass_f(fs, 0), fb = pass_f(fs, 1), fc = pass_f(fs, 2);
#define BAR(i) (sb + M_BAR + 8 * (i))
#define kh (j & 1)
            int sl = 0;
            mbar_wait(BAR(B_PUB + 2), 0);
            wait_flags(g_flag + (8 * r + j) * 128 + 96 + lane, lds1(sb + M_EPOCH) + 1, 0xFFFFu);
            fence_async_global();
#pragma unroll 1
            for (int s = 0; s < 28; s++) {
                const int ps = s < 14 ? 0 : s < 21 ? 1 : 2;
                const uint32_t half = ps < 2 ? 8192 : 4096;
                const int sp = s >= 3 && s < 7 ? (s == 6 ? 3 : s + 1) : sl;
                mbar_wait(BAR(B_EMPTY + sp), (s >= 7 && s < 14) || s >= 21);
                expect_e(BAR(B_FULL + sp), half);
                tma3_e(sb + slot_off(sp) + sec * half, &p.ga + 2 * ps + sec, 0, ps ? 64 * sl : 32 * s, ps == 0 ? fa >> 6 : ps == 1 ? fb >> 6 : fc >> 5, BAR(B_FULL + sp));
                sl = sl == 6 ? 0 : sl + 1;
            }
            if (!sec) PROFH(3);
#pragma unroll 1
            for (int e = 0; e < 4; e++) {
                const uint32_t dst = sb + slot_off(e) + sec * 8192, bar = BAR(B_FULL + e);
                const int f = (e < 2 ? fa + 64 * e : e == 2 ? fb : fc) + 32 * sec;
                mbar_wait(BAR(B_EMPTY + e), 0);
                expect_e(bar, e == 3 && sec ? 0 : 7168);
                if (!(e == 3 && sec)) { LOADW }
            }
            sl = 4;
            int e = 4;
#pragma unroll 1
            for (int grp = 0; grp < 9; grp++) {
                const int ps = grp >= 6 ? 2 : grp >= 3 ? 1 : 0;
                int sidx = grp - 3 * ps;
                if (sec && sidx == 0) { mbar_wait(BAR(B_HRDY + ps), 0); fence_async_global(); }
                sidx += sidx >= nq;
                int f = pass_f(4 * kh + sidx, ps);
#pragma unroll 1
                for (int k = 4 >> ps; k > 0; k--, e++, f += 32) {
                    const uint32_t dst = sb + slot_off(sl), bar = BAR(B_FULL + sl);
                    mbar_wait(BAR(B_EMPTY + sl), e >= 12 && e < 24);
                    if (e < WIN_END && e >= WIN) mbar_wait(BAR(B_FULL + (sl >= WIN ? sl - WIN : sl + 12 - WIN)), e - WIN >= 12);
                    expect_e(bar, sec ? 8192 : 7168);
                    if (!sec) { LOADW }
                    else bulk_e(dst + 8192, p.actb + (size_t)r * RB_WORDS + RB_H2 + f * 64, 8192, bar);
                    sl = sl == 11 ? 0 : sl + 1;
                }
            }
            if (!sec) PROFH(4);
}

__global__ void __cluster_dims__(2, 1, 1) __launch_bounds__(384, 1) fused_block_kernel(const __grid_constant__ Params p) {
    extern __shared__ __align__(1024) unsigned char smem[];
    const uint32_t sb = (uint32_t)__cvta_generic_to_shared(smem);
    const int tid = threadIdx.x, lane = tid & 31, warp = __shfl_sync(~0u, tid >> 5, 0);
    const int m = blockIdx.x >> 1;
    int r, nq;
    {
        int g, i;
        if (m < MAP_S) { g = m < 4 ? 15 : 16; i = m & 3; }
        else if (m < MAP_S + 32) { g = (m - MAP_S) & 7; i = (m - MAP_S) >> 3; }
        else if (m < MAP_S + 60) { i = (m - MAP_S - 32) / 7; g = 8 + (m - MAP_S - 32) - 7 * i; }
        else { g = 16; i = m & 3; }
        r = g; nq = i;
    }
    const int j = opaque(2 * nq + (blockIdx.x & 1)), b = 8 * r + j, fs = 4 * kh + nq;
#define act (p.actb + (size_t)r * RB_WORDS)
    const uint32_t sc = r == 16;
    if (lane == 0 && warp < 9 && warp != 6 && warp != 7) {
        const int i0 = warp == 8 ? 0 : 8 + 8 * warp, cnt = warp == 0 || warp == 8 ? 1 : warp < 3 ? 2 : 8;
#pragma unroll
        for (int k = 0; k < 8; k++) if (i0 + k != B_WMFULL) mbar_init(BAR(i0 + k), cnt);
        asm volatile("fence.mbarrier_init.release.cluster;" ::: "memory");
        fence_async_smem();
    }

    if (warp < 8) {
        const int w = warp >> 2, wi = warp & 3;
#define COORDS const int t = fresh_tid() & 127, lane = t & 31, q = lane & 3, lr = lane >> 2, ra = 64 * w + 16 * wi + lr; \
        const uint32_t lx = (lane >> 4) ^ (lane & 7), mrow = (64 * w + 16 * wi + ((lane >> 3) & 1) * 8 + (lane & 7)) * 128; \
        (void)q; (void)lr; (void)ra; (void)lx; (void)mrow;
        const int sid = 2 * (j & 3) + w;
#define RUN(k) (!sc || sid == (k))
#define WAIT(i, par) mbar_wait_c(BAR(i), (par) | sc)
        constexpr uint64_t DB128 = dconst(4096, 1024, 1);
        {
            const int wd = fresh_tid();
            const uint32_t cb = wd < 224 ? __ldg((const uint32_t*)p.c + wd) : 0u;
            if (wd == 255 && !sc) sts1(sb + M_EPOCH, atomicAdd(&g_ticket, 1u) / NCTA);
            sts1(sb + OFF_Y + HALF + 28672 + (wd >> 3) * 32 + (wd & 3) * 8 + (wd & 4), pack2(silu_bf(cb & 0xFFFFu), silu_bf(cb >> 16)));
        }
        bar_arrive(9, 384);
        bar_sync(0, 384);
        asm volatile("barrier.cluster.arrive.relaxed.aligned;" ::: "memory");
        asm volatile("setmaxnreg.inc.sync.aligned.u32 224;");
        PROFC(0);
        uint32_t xr[16];
        {
            COORDS
            uint32_t h[112];
            if (RUN(0)) {
                float ds[4] = {}, da[2][4] = {}, db[2][4] = {};
                const uint32_t ONE2 = 0x3F803F80u;
                if (kh == 0) { WAIT(B_WMFULL, 0); gemv_part(sb + OFF_Y + HALF, 1, warp, lane); warp_arrive(BAR(B_GEMV)); }
#pragma unroll
                for (int kb = 0; kb < 7; kb++) {
                    WAIT(B_XFULL + kb, 0);
#pragma unroll
                    for (int k4 = 0; k4 < 4; k4++) ldsm4(sb + OFF_X + mrow + kb * 16384 + (((2 * k4) ^ lx) << 4), h + 16 * kb + 4 * k4);
#pragma unroll
                    for (int k4 = 0; k4 < 4; k4++) {
                        const uint32_t* f = h + 16 * kb + 4 * k4;
                        mma16816(ds, f[0], f[1], f[2], f[3], ONE2, ONE2);
                        mma1688(da[0], f[0], f[1], f[0]); mma1688(db[0], f[0], f[1], f[1]);
                        mma1688(da[1], f[2], f[3], f[2]); mma1688(db[1], f[2], f[3], f[3]);
                    }
                }
#pragma unroll
                for (int i = 0; i < 4; i++) {
                    const int ch = 7 * j + 2 * i + (lane >> 4);
                    ldsm4(sb + OFF_X + mrow + (ch >> 3) * 16384 + (((ch ^ lane) & 7) << 4), xr + 4 * i);
                }
                warp_arrive(BAR(B_XFREE));
                float qa = (lr & 1) ? da[0][1] + da[1][1] : da[0][0] + da[1][0];
                float qb = (lr & 1) ? db[0][3] + db[1][3] : db[0][2] + db[1][2];
                const int src = (lane & ~3) | (lr >> 1);
                qa = __shfl_sync(~0u, qa, src);
                qb = __shfl_sync(~0u, qb, src);
                uint32_t ra2, na2, rb2, nb2;
                ln_coeffs(ds[0] * (1.f / DM), qa * (1.f / DM), ra2, na2);
                ln_coeffs(ds[2] * (1.f / DM), qb * (1.f / DM), rb2, nb2);
#pragma unroll
                for (int i = 0; i < 112; i += 2) { h[i] = hfma2(h[i], ra2, na2); h[i + 1] = hfma2(h[i + 1], rb2, nb2); }
                if (kh == 1) { WAIT(B_WMFULL, 0); gemv_part(sb + OFF_Y + HALF, 2, warp, lane); warp_arrive(BAR(B_GEMV)); }
            } else { reg_def<112>(h); reg_def<16>(xr); }
            PROFC(1);
            if (RUN(1)) {
                float ak[28], av[28], aq[28];
                uint32_t kp[14], vp[14];
                const uint32_t bk0 = mkdesc(sb + OFF_Y, DB128) + kh, bv0 = mkdesc(sb + OFF_Y + HALF, DB128) + kh, bq0 = mkdesc(sb + OFF_X, DB128) + kh;
                uint32_t* kvg = act + RB_KV + j * 7168 + (8 * w + 2 * wi) * 224 + lane;
                {
                    const int i = min(fresh_tid(), 223);
                    const uint4* src = mod_src(i, r, j, false);
                    mod_store(sb, ld_relaxed4(src), src, i, sc);
                    if (!sc) bar_sync(3, 256);
                    if (warp == 0) warp_arrive(BAR(B_MOD1));
                }
                WAIT(B_FULLK, 0);
                PROFC(2);
                reg_def<28>(ak);
#pragma unroll
                for (int g4 = 0; g4 < 4; g4++) {
#pragma unroll
                    for (int ks = 7 * g4; ks < 7 * g4 + 7; ks++) {
                        const uint4 st = *(const uint4*)(smem + M_ST + ks * 64 + q * 16);
                        h[4 * ks] = hfma2(h[4 * ks], st.x, st.y); h[4 * ks + 1] = hfma2(h[4 * ks + 1], st.x, st.y);
                        h[4 * ks + 2] = hfma2(h[4 * ks + 2], st.z, st.w); h[4 * ks + 3] = hfma2(h[4 * ks + 3], st.z, st.w);
                    }
                    WG_FENCE();
#pragma unroll
                    for (int ks = 7 * g4; ks < 7 * g4 + 7; ks++) wgmma_rs_56<DB128>(ak, h[4 * ks], h[4 * ks + 1], h[4 * ks + 2], h[4 * ks + 3], bk0 + ks * 128, ks != 0);
                }
                WG_COMMIT();
                PROFC(3);
                WAIT(B_FULLV, 0);
                reg_def<28>(av);
                WG_FENCE();
#pragma unroll
                for (int ks = 0; ks < 8; ks++) wgmma_rs_56<DB128>(av, h[4 * ks], h[4 * ks + 1], h[4 * ks + 2], h[4 * ks + 3], bv0 + ks * 128, ks != 0);
                WG_COMMIT();
                WG_WAIT(1);
                reg_fence<28>(ak);
#pragma unroll
                for (int g = 0; g < 7; g++) {
                    kp[2 * g] = pack2(ak[4 * g], ak[4 * g + 1]); kp[2 * g + 1] = pack2(ak[4 * g + 2], ak[4 * g + 3]);
                    kvg[g * 32] = kp[2 * g]; kvg[224 + g * 32] = kp[2 * g + 1];
                }
                warp_arrive(BAR(B_PUB));
                PROFC(4);
                WG_FENCE();
#pragma unroll
                for (int ks = 8; ks < 28; ks++) wgmma_rs_56<DB128>(av, h[4 * ks], h[4 * ks + 1], h[4 * ks + 2], h[4 * ks + 3], bv0 + ks * 128, 1);
                WG_COMMIT();
                WAIT(B_FULLQ, 0);
                reg_def<28>(aq);
                WG_FENCE();
#pragma unroll
                for (int ks = 0; ks < 8; ks++) wgmma_rs_56<DB128>(aq, h[4 * ks], h[4 * ks + 1], h[4 * ks + 2], h[4 * ks + 3], bq0 + ks * 128, ks != 0);
                WG_COMMIT();
                WG_WAIT(1);
                reg_fence<28>(av);
#pragma unroll
                for (int g = 0; g < 7; g++) {
                    vp[2 * g] = pack2(av[4 * g], av[4 * g + 1]); vp[2 * g + 1] = pack2(av[4 * g + 2], av[4 * g + 3]);
                    kvg[3584 + g * 32] = vp[2 * g]; kvg[3584 + 224 + g * 32] = vp[2 * g + 1];
                }
                warp_arrive(BAR(B_PUB + 1));
                const uint4* msrc = mod_src(128 * w + t, r, j, true);
                const uint4 mv = ld_relaxed4(msrc);
                PROFC(5);
                WG_FENCE();
#pragma unroll
                for (int ks = 8; ks < 28; ks++) wgmma_rs_56<DB128>(aq, h[4 * ks], h[4 * ks + 1], h[4 * ks + 2], h[4 * ks + 3], bq0 + ks * 128, 1);
                WG_COMMIT();
                WAIT(B_PUB + 1, 0);
                mod_store(sb, mv, msrc, 128 * w + t, sc);
                const uint32_t ko = sb + OFF_Y + Y_KOWN + (8 * w + 2 * wi) * 896 + lane * 4;
                const uint32_t qo = sb + OFF_Y + Y_Q + (8 * w + 2 * wi) * 1024 + lane * 4;
#pragma unroll
                for (int g = 0; g < 7; g++) {
                    sts1(ko + g * 128, kp[2 * g]); sts1(ko + 896 + g * 128, kp[2 * g + 1]);
                    sts1(ko + (Y_VOWN - Y_KOWN) + g * 128, vp[2 * g]); sts1(ko + (Y_VOWN - Y_KOWN) + 896 + g * 128, vp[2 * g + 1]);
                }
                WG_WAIT(0);
                reg_fence<28>(aq);
                __syncwarp();
                if (lane < 3 && w == 1) mbar_arrive(BAR(B_EMPTY + lane));
#pragma unroll
                for (int g = 0; g < 7; g++) {
                    const uint32_t q0 = pack2(aq[4 * g], aq[4 * g + 1]), q1 = pack2(aq[4 * g + 2], aq[4 * g + 3]);
                    if (g == 3) {
                        sts1(qo + 3 * 128, q < 2 ? q0 : 0u); sts1(qo + 1024 + 3 * 128, q < 2 ? q1 : 0u);
                        sts1(qo + 4 * 128, q < 2 ? 0u : q0); sts1(qo + 1024 + 4 * 128, q < 2 ? 0u : q1);
                    } else {
                        const int ch = g < 3 ? g : g + 1;
                        sts1(qo + ch * 128, q0); sts1(qo + 1024 + ch * 128, q1);
                    }
                }
                if (!sc) bar_sync(3, 256);
            }
        }
        PROFC(6);
        WAIT(B_KRFULL, 0);
        PROFC(7);
        if (RUN(2)) {
#pragma unroll 1
            for (int hf = sc; hf < 2; hf++) {
                COORDS
                float s[136];
                float na = 0.f, nb = 0.f;
                const float CS = 0.18898223650461361f * 1.4426950408889634f;
                const int kg0 = 8 * hf + 2 * wi;
                const int pmin = 16 - 8 * r - 4 * hf - wi;
                const float NEG = __int_as_float(0xFF800000);
                {
                    uint32_t F[8];
                    const uint32_t qa = sb + OFF_Y + Y_Q + (kg0 + ((lane >> 3) & 1)) * 1024 + (4 * w + (lane >> 4)) * 128 + (lane & 7) * 16;
                    ldsm4(qa, F); ldsm4(qa + 256, F + 4);
                    uint32_t ka = sb + OFF_Y + Y_K + kg0 * 896 + (3 * w + (lane >> 3)) * 128 + (lane & 7) * 16;
#pragma unroll
                    for (int g = 0; g < 34; g++) {
                        uint32_t B[4];
                        if (g >= 12 && g % 4 == 0) ka += __float_as_uint(s[4 * (g - 12)]) & p.zero;
                        ldsm4(ka + g * 896, B);
                        mma16816_first(s + 4 * g, F[0], F[1], F[2], F[3], B[0], B[1]);
                        mma16816_v(s + 4 * g, F[4], F[5], F[6], F[7], B[2], B[3]);
                    }
                    const bool c0 = 2 * q > lr, c1 = 2 * q + 1 > lr;
                    if (!c0) { s[0] = NEG; s[6] = NEG; }
                    if (!c1) { s[1] = NEG; s[7] = NEG; }
                    s[2] = NEG; s[3] = NEG;
                    if (c0) { s[128] = NEG; s[134] = NEG; }
                    if (c1) { s[129] = NEG; s[135] = NEG; }
                    s[132] = NEG; s[133] = NEG;
                    float ma = NEG, mb = NEG;
#pragma unroll
                    for (int pp = 0; pp < 17; pp++) {
                        const float* e = s + 8 * pp;
                        const float bias = pp < pmin ? NEG : 0.f;
                        ma = fmaxf(ma, fmaxf(fmaxf(e[0], e[1]), fmaxf(e[4], e[5])) + bias);
                        mb = fmaxf(mb, fmaxf(fmaxf(e[2], e[3]), fmaxf(e[6], e[7])) + bias);
                    }
                    ma = fmaxf(ma, __shfl_xor_sync(~0u, ma, 1)); mb = fmaxf(mb, __shfl_xor_sync(~0u, mb, 1));
                    ma = fmaxf(ma, __shfl_xor_sync(~0u, ma, 2)); mb = fmaxf(mb, __shfl_xor_sync(~0u, mb, 2));
                    na = -ma * CS; nb = -mb * CS;
                }
                PROFC(8 + 3 * hf);
                {
                    WAIT(B_VRFULL, 0);
                    float o[16] = {}, rs[4] = {};
                    uint32_t pk[2];
                    const uint32_t va = sb + OFF_Y + Y_VR + (kg0 + ((lane >> 3) & 1)) * 896 + (3 * w + (lane >> 4)) * 128 + (lane & 7) * 16;
#pragma unroll
                    for (int pp = 0; pp < 17; pp++) {
                        uint32_t B[8];
                        const uint32_t v = va + pp * 1792 + (pp == 16 || (pp >= 9 && kg0 + 2 * pp >= 32) ? Y_VOWN - 32 * 896 : 0);
                        ldsm4t(v, B); ldsm4t(v + 256, B + 4);
                        float e[8];
                        const float bias = __uint_as_float((pp < pmin ? 0xFF800000u : 0u) | ((pp < 2 ? B[0] : pk[pp & 1]) & p.zero));
#pragma unroll
                        for (int i = 0; i < 8; i++) e[i] = ex2(fmaf(s[8 * pp + i], CS, ((i & 2) ? nb : na) + bias));
                        const uint32_t p0 = pack2(e[0], e[1]), p1 = pack2(e[2], e[3]), p2 = pack2(e[4], e[5]), p3 = pack2(e[6], e[7]);
                        pk[pp & 1] = p3;
                        mma16816(rs, p0, p1, p2, p3, 0x3F803F80u, 0x3F803F80u);
#pragma unroll
                        for (int g = 0; g < 4; g++) mma16816(o + 4 * g, p0, p1, p2, p3, B[2 * g], B[2 * g + 1]);
                    }
                    PROFC(9 + 3 * hf);
                    const float ia = rcp(rs[0]), ib = rcp(rs[2]);
                    uint32_t* og = act + RB_O + hf * 14336 + (7 * j + 3 * w) * 256 + wi * 64 + lane;
#pragma unroll
                    for (int g = 0; g < 4; g++) {
                        if ((g == 3 - 3 * w) ? ((q >> 1) == w) : true) {
                            og[g * 256] = pack2(o[4 * g] * ia, o[4 * g + 1] * ia);
                            og[g * 256 + 32] = pack2(o[4 * g + 2] * ib, o[4 * g + 3] * ib);
                        }
                    }
                    warp_arrive(BAR(B_PUB + 2 + hf));
                    PROFC(10 + 3 * hf);
                }
            }
        }
        uint32_t x1p[14];
        COORDS
        constexpr uint64_t DT = dconst(1024, 128, 0);
        const int tile = opaque((lds1(sb + M_EPOCH) & 1) * 2 + w);
        if (RUN(4)) {
            float ac[28];
            const uint32_t ad = mkdesc(sb + (w ? OFF_Y + HALF : OFF_X), DT), bd = mkdesc(sb + OFF_X + HALF, DB128) + kh;
            WAIT(B_WOFULL, 0);
            WAIT(B_GFULL + w, 0);
            PROFC(28);
            reg_def<28>(ac);
#pragma unroll 1
            for (int u = 0; u < 4; u++) {
                if (u == 2) WAIT(B_XFULL + 2 + w, 1);
                WG_FENCE();
#pragma unroll
                for (int i = 0; i < 7; i++) wgmma_ss_56<DT, DB128>(ac, ad + (7 * u + i) * 128, bd + (7 * u + i) * 128, (u | i) != 0);
            }
            WG_COMMIT();
            WG_WAIT(0);
            reg_fence<28>(ac);
            PROFC(14);
            __syncwarp();
            if (lane < 3) mbar_arrive(BAR(B_EMPTY + 4 + lane));
            if (lane < 3 && w == 0) mbar_arrive(BAR(B_EMPTY + lane));
            float s1a = 0.f, s2a = 0.f, s1b = 0.f, s2b = 0.f;
            uint32_t* xo = act + RB_X1 + tile * 14336 + 7 * j * 256 + wi * 64 + lane;
#pragma unroll
            for (int g = 0; g < 7; g++) {
                const float2 ga = *(const float2*)(smem + M_G + (8 * g + 2 * q) * 4);
                x1p[2 * g] = pack2(fmaf(ga.x, ac[4 * g], bf_lo(xr[2 * g])), fmaf(ga.y, ac[4 * g + 1], bf_hi(xr[2 * g])));
                x1p[2 * g + 1] = pack2(fmaf(ga.x, ac[4 * g + 2], bf_lo(xr[2 * g + 1])), fmaf(ga.y, ac[4 * g + 3], bf_hi(xr[2 * g + 1])));
                st_relaxed(xo + g * 256, max(x1p[2 * g], 1u)); st_relaxed(xo + g * 256 + 32, max(x1p[2 * g + 1], 1u));
                const float u0 = bf_lo(x1p[2 * g]), u1 = bf_hi(x1p[2 * g]), u2 = bf_lo(x1p[2 * g + 1]), u3 = bf_hi(x1p[2 * g + 1]);
                s1a += u0 + u1; s2a += u0 * u0 + u1 * u1; s1b += u2 + u3; s2b += u2 * u2 + u3 * u3;
            }
            float ka = (q & 1) ? s2a : s1a, kb2 = (q & 1) ? s2b : s1b;
            ka += __shfl_xor_sync(~0u, (q & 1) ? s1a : s2a, 1); kb2 += __shfl_xor_sync(~0u, (q & 1) ? s1b : s2b, 1);
            const float kk = ((q & 2) ? kb2 : ka) + __shfl_xor_sync(~0u, (q & 2) ? ka : kb2, 2);
            st_relaxed(act + RB_ST + ((tile * 8 + j) * 64 + 16 * wi + lr + 4 * (q & 2)) * 2 + (q & 1), max(__float_as_uint(kk), 1u));
            __syncwarp();
            if (lane < 2) mbar_arrive(BAR(B_PUB + 4 + w));
        } else reg_def<14>(x1p);
        PROFC(15);
        uint32_t h2a[32], h2b[24];
        {
            const int fa = pass_f(fs, 0), fb = pass_f(fs, 1), fc = pass_f(fs, 2);
            uint32_t* h2g = act + RB_H2 + (8 * w + 2 * wi) * 32 + lane;
            const uint32_t a0 = mkdesc(sb + OFF_Y + w * HALF, DT);
            if (RUN(3)) {
                uint32_t ra2, na2, rb2, nb2;
                {
                    const uint32_t* sg = act + RB_ST + ((tile * 8 + 2 * q) * 64 + 16 * wi + lr) * 2;
                    uint2 u[4];
                    WAIT(B_GFULL + 2 + w, 0);
                    PROFC(16);
#pragma unroll
                    for (int i = 0; i < 4; i++) { const float2 v = lds2f(sb + OFF_X + X_STAT + w * 4096 + ((2 * q + (i >> 1)) * 64 + 16 * wi + lr + 8 * (i & 1)) * 8); u[i] = make_uint2(__float_as_uint(v.x), __float_as_uint(v.y)); }
                    while (__any_sync(~0u, min(min(min(u[0].x, u[0].y), min(u[1].x, u[1].y)), min(min(u[2].x, u[2].y), min(u[3].x, u[3].y))) < 1u - sc)) {
#pragma unroll
                        for (int i = 0; i < 4; i++) u[i] = ld_relaxed2(sg + (i >> 1) * 128 + (i & 1) * 16);
                    }
                    warp_arrive(BAR(B_EMPTY + 3));
                    float v[4] = {__uint_as_float(u[0].x) + __uint_as_float(u[2].x), __uint_as_float(u[0].y) + __uint_as_float(u[2].y),
                                  __uint_as_float(u[1].x) + __uint_as_float(u[3].x), __uint_as_float(u[1].y) + __uint_as_float(u[3].y)};
#pragma unroll
                    for (int i = 0; i < 4; i++) { v[i] += __shfl_xor_sync(~0u, v[i], 1); v[i] += __shfl_xor_sync(~0u, v[i], 2); }
                    ln_coeffs(v[0] * (1.f / DM), v[1] * (1.f / DM), ra2, na2);
                    ln_coeffs(v[2] * (1.f / DM), v[3] * (1.f / DM), rb2, nb2);
                }
                const uint32_t ha = sb + OFF_Y + w * HALF + (lane >> 4) * 1024 + (2 * wi + ((lane >> 3) & 1)) * 128 + (lane & 7) * 16;
                const uint32_t sta = sb + M_ST + q * 16;
                const uint32_t* xg = act + RB_X1 + tile * 14336 + (lane >> 4) * 256 + wi * 64 + (lane & 15) * 4;
                uint32_t x[8];
                const uint32_t xs = sb + OFF_Y + w * HALF + (lane >> 4) * 1024 + wi * 256 + (lane & 15) * 16;
                uint4 st[2];
                auto load = [&](int s) {
                    if (s == 0) x1_check(xg, xs, 16, sc);
                    if (s == 4) { mbar_wait_c(BAR(B_XFULL + 4 + w), 1); x1_check(xg + 4096, xs + 16384, 40, sc); }
                    ldsm4(ha + s * 4096, x); ldsm4(ha + s * 4096 + 2048, x + 4);
                    st[0] = lds4(sta + s * 128); st[1] = lds4(sta + s * 128 + 64);
                };
                auto prep = [&](int s, uint32_t* f) {
#pragma unroll
                    for (int i = 0; i < 2; i++) {
                        f[4 * i] = hfma2(hfma2(x[4 * i], ra2, na2), st[i].x, st[i].y); f[4 * i + 1] = hfma2(hfma2(x[4 * i + 1], rb2, nb2), st[i].x, st[i].y);
                        f[4 * i + 2] = hfma2(hfma2(x[4 * i + 2], ra2, na2), st[i].z, st[i].w); f[4 * i + 3] = hfma2(hfma2(x[4 * i + 3], rb2, nb2), st[i].z, st[i].w);
                    }
                    if (s < 13) load(s + 1);
                    stsm4(ha + s * 4096, f[0], f[1], f[2], f[3]); stsm4(ha + s * 4096 + 2048, f[4], f[5], f[6], f[7]);
                };
                float ac[128];
                uint32_t fr[3][8];
                const uint32_t bx = mkdesc(sb, DB128);
                reg_def<128>(ac);
                load(0);
                prep(0, fr[0]);
                PROFC(17);
#pragma unroll
                for (int s = 0; s < 14; s++) {
                    const uint32_t* f = fr[s % 3];
                    const uint32_t bd = bx + g1_slot(s) * 1024;
                    WAIT(B_FULL + g1_slot(s), s >= 7);
                    WG_FENCE();
                    wgmma_rs_256<DB128>(ac, f[0], f[1], f[2], f[3], bd, s != 0);
                    wgmma_rs_256<DB128>(ac, f[4], f[5], f[6], f[7], bd + 128, 1);
                    WG_COMMIT();
                    if (s < 13) prep(s + 1, fr[(s + 1) % 3]);
                    if (s > 0) { WG_WAIT(1); warp_arrive(BAR(B_EMPTY + g1_slot(s - 1))); }
                }
                fence_async_smem();
                PROFC(18);
                WG_WAIT(0);
                reg_fence<128>(ac);
                warp_arrive(BAR(B_EMPTY + 6));
#pragma unroll
                for (int g = 0; g < 16; g++) {
                    h2a[2 * g] = hmul2(pack2_relu(ac[4 * g], ac[4 * g + 1]), pack2(ac[64 + 4 * g], ac[64 + 4 * g + 1]));
                    h2a[2 * g + 1] = hmul2(pack2_relu(ac[4 * g + 2], ac[4 * g + 3]), pack2(ac[64 + 4 * g + 2], ac[64 + 4 * g + 3]));
                    h2g[(fa / 8 + g) * 512] = h2a[2 * g]; h2g[(fa / 8 + g) * 512 + 32] = h2a[2 * g + 1];
                }
                warp_arrive(BAR(B_PUB + 6));
                bar_sync(1 + w, 128);
            } else reg_def<32>(h2a);
            PROFC(19);
            if (RUN(5)) {
                float ac[64];
                reg_def<64>(ac);
                const uint32_t bx = mkdesc(sb, dconst(8192, 1024, 1));
#pragma unroll kB
                for (int s = 0; s < 7; s++) {
                    WAIT(B_FULL + s, 0);
                    const uint32_t ad = a0 + s * 512, bd = bx + (slot_off(s) >> 4);
                    WG_FENCE();
#pragma unroll
                    for (int k = 0; k < 4; k++) wgmma_ss_128<DT, DB128>(ac, ad + k * 128, bd + k * 128, (s | k) != 0);
                    WG_COMMIT();
                    if (s > 0) { WG_WAIT(1); warp_arrive(BAR(B_EMPTY + s - 1)); }
                }
                WG_WAIT(0);
                reg_fence<64>(ac);
                warp_arrive(BAR(B_EMPTY + 6));
#pragma unroll
                for (int g = 0; g < 8; g++) {
                    h2b[2 * g] = hmul2(pack2_relu(ac[4 * g], ac[4 * g + 1]), pack2(ac[32 + 4 * g], ac[32 + 4 * g + 1]));
                    h2b[2 * g + 1] = hmul2(pack2_relu(ac[4 * g + 2], ac[4 * g + 3]), pack2(ac[32 + 4 * g + 2], ac[32 + 4 * g + 3]));
                    h2g[(fb / 8 + g) * 512] = h2b[2 * g]; h2g[(fb / 8 + g) * 512 + 32] = h2b[2 * g + 1];
                }
                warp_arrive(BAR(B_PUB + 7));
            } else reg_def<16>(h2b);
            PROFC(27);
            if (RUN(6)) {
                float ac[32];
                reg_def<32>(ac);
                const uint32_t bx = mkdesc(sb, dconst(4096, 512, 2));
#pragma unroll kC
                for (int s = 0; s < 7; s++) {
                    WAIT(B_FULL + s, 1);
                    const uint32_t ad = a0 + s * 512, bd = bx + (slot_off(s) >> 4);
                    WG_FENCE();
#pragma unroll
                    for (int k = 0; k < 4; k++) wgmma_ss_64<DT, dconst(4096, 512, 2)>(ac, ad + k * 128, bd + k * 64, (s | k) != 0);
                    WG_COMMIT();
                    if (s > 0) { WG_WAIT(1); warp_arrive(BAR(B_EMPTY + s - 1)); }
                }
                WG_WAIT(0);
                reg_fence<32>(ac);
                __syncwarp();
                if (lane < 6) mbar_arrive(BAR(B_EMPTY + 6 + lane));
                PROFC(20);
#pragma unroll
                for (int g = 0; g < 4; g++) {
                    h2b[16 + 2 * g] = hmul2(pack2_relu(ac[4 * g], ac[4 * g + 1]), pack2(ac[16 + 4 * g], ac[16 + 4 * g + 1]));
                    h2b[16 + 2 * g + 1] = hmul2(pack2_relu(ac[4 * g + 2], ac[4 * g + 3]), pack2(ac[16 + 4 * g + 2], ac[16 + 4 * g + 3]));
                    h2g[(fc / 8 + g) * 512] = h2b[16 + 2 * g]; h2g[(fc / 8 + g) * 512 + 32] = h2b[16 + 2 * g + 1];
                }
                warp_arrive(BAR(B_PUB + 8));
                asm volatile("barrier.cluster.wait.aligned;" ::: "memory");
                if (lane == 0 && !sc) {
                    uint32_t rb;
                    asm volatile("mapa.shared::cluster.u32 %0, %1, %2;" : "=r"(rb) : "r"(BAR(B_PEER)), "r"(kh ^ 1));
                    asm volatile("mbarrier.arrive.relaxed.cluster.shared::cluster.b64 _, [%0];" ::"r"(rb) : "memory");
                }
            } else reg_def<8>(h2b + 16);
        }
        PROFC(21);
        if (RUN(7)) {
            float ac[56];
            reg_def<56>(ac);
            constexpr uint64_t DAN = dconst(2048, 128, 0);
            constexpr uint64_t DW = dconst(128, 512, 0);
            const uint32_t bx = mkdesc(sb, DW);
#pragma unroll
            for (int e = 0; e < 4; e++) {
                WAIT(B_FULL + e, 0);
                const uint32_t bd = bx + (slot_off(e) >> 4);
                const uint32_t* hh = e < 2 ? h2a + 16 * e : h2b + 16 * (e - 2);
                WG_FENCE();
#pragma unroll
                for (int k = 0; k < (e < 3 ? 4 : 2); k++) wgmma_rs_112<DW>(ac, hh[4 * k], hh[4 * k + 1], hh[4 * k + 2], hh[4 * k + 3], bd + (k >> 1) * 512 + (k & 1) * 16, (e | k) != 0);
                WG_COMMIT();
                if (e > 0) { WG_WAIT(1); warp_arrive(BAR(B_EMPTY + e - 1)); }
            }
            PROFC(22);
            uint32_t ad = mkdesc(sb + 4 * 16384 + 8192 + w * 1024, DAN), bd = bx + 4 * 1024, fb_ = BAR(B_FULL + 4), eb_ = BAR(B_EMPTY + 3), par = sc;
#pragma unroll 1
            for (int e = 4; e < 25; e++) {
                mbar_wait_c(fb_, par);
                WG_FENCE();
                wgmma_ss_112<DAN, DW>(ac, ad, bd, 1);
                wgmma_ss_112<DAN, DW>(ac, ad + 256, bd + 16, 1);
                WG_COMMIT();
                WG_WAIT(1);
                warp_arrive(eb_);
                eb_ = fb_ + 8 * (B_EMPTY - B_FULL);
                ad += 1024; bd += 1024; fb_ += 8;
                if (e == 11 || e == 23) { ad -= 12 * 1024; bd -= 12 * 1024; fb_ -= 96; par = (par ^ 1) | sc; }
            }
            mbar_wait_cluster(BAR(B_PEER), sc);
            WG_WAIT(0);
            reg_fence<56>(ac);
            PROFC(24);
            uint32_t rdst, rbar;
            asm volatile("mapa.shared::cluster.u32 %0, %1, %2;" : "=r"(rdst) : "r"(sb + OFF_Y + (5 + w) * 16384 + t * 16), "r"(kh ^ 1 ^ sc));
            asm volatile("mapa.shared::cluster.u32 %0, %1, %2;" : "=r"(rbar) : "r"(BAR(B_XCH + w)), "r"(kh ^ 1 ^ sc));
#pragma unroll
            for (int g = 0; g < 7; g++) {
                const float v0 = ac[28 + 4 * g + 0], v1 = ac[28 + 4 * g + 1];
                const float v2 = ac[28 + 4 * g + 2], v3 = ac[28 + 4 * g + 3];
                if (!sc) asm volatile("st.async.shared::cluster.mbarrier::complete_tx::bytes.v4.f32 [%0], {%1,%2,%3,%4}, [%5];"
                             ::"r"(rdst + g * 2048), "f"(v0), "f"(v1), "f"(v2), "f"(v3), "r"(rbar) : "memory");
            }
            mbar_wait_cluster(BAR(B_XCH + w), sc);
            PROFC(25);
            bf16* og = (sc ? (bf16*)act : p.out + (size_t)128 * r * DM) + (size_t)ra * DM + 56 * j + 2 * q;
#pragma unroll
            for (int g = 0; g < 7; g++) {
                const uint4 rv = *(const uint4*)(smem + OFF_Y + (5 + w) * 16384 + t * 16 + g * 2048);
                const float2 gb = *(const float2*)(smem + M_G + 224 + (8 * g + 2 * q) * 4);
                const float v0 = ac[4 * g + 0] + __uint_as_float(rv.x), v1 = ac[4 * g + 1] + __uint_as_float(rv.y);
                const float v2 = ac[4 * g + 2] + __uint_as_float(rv.z), v3 = ac[4 * g + 3] + __uint_as_float(rv.w);
                *(uint32_t*)(og + 8 * g) = pack2(fmaf(gb.x, v0, bf_lo(x1p[2 * g])), fmaf(gb.y, v1, bf_hi(x1p[2 * g])));
                *(uint32_t*)(og + 8 * DM + 8 * g) = pack2(fmaf(gb.x, v2, bf_lo(x1p[2 * g + 1])), fmaf(gb.y, v3, bf_hi(x1p[2 * g + 1])));
            }
        }
        PROFC(26);
        bar_sync(1 + w, 128);
        if (wi == 0) warp_arrive(BAR(B_DONE));
    } else {
        const int lane = fresh_tid() & 31;
        const bool early = kh == 0, gemv = r < 14;
        const int mcol = early ? 16 * (4 * r + nq) : 2 * DM + 32 * (4 * r + nq);
        const uint32_t wmbuf = sb + OFF_Y + HALF;
        asm volatile("setmaxnreg.dec.sync.aligned.u32 56;");
        if (warp == 9) {
#pragma unroll
            for (int i = 56; i < 64; i++) init_e(BAR(i), 1);
            fence_async_smem();
        }
        if (warp == 8) { init_e(BAR(B_WMFULL), 1); fence_async_smem(); }
        bar_arrive(0, 384);
        asm volatile("barrier.cluster.arrive.relaxed.aligned;" ::: "memory");
        uint32_t target = 0;
        if (warp == 8) {
            if (!sc) {
                expect_e(BAR(B_WMFULL), gemv ? 28672 >> early : 0);
                if (early && gemv) { tma3_e(wmbuf, &p.wm, mcol, 0, 0, BAR(B_WMFULL)); tma3_e(wmbuf + 7168, &p.wm, mcol, 224, 0, BAR(B_WMFULL)); }
#pragma unroll 1
                for (int kb = 0; kb < 7; kb++) {
                    expect_e(BAR(B_XFULL + kb), 16384);
                    tma3_e(sb + OFF_X + kb * 16384, &p.xm, 64 * kb, 128 * r, 0, BAR(B_XFULL + kb));
                }
            }
#pragma unroll 1
            for (int mt = 0; mt < 4; mt++) {
                if (mt == 1) {
                    if (!early && gemv) {
#pragma unroll 1
                        for (int k = 0; k < 4; k++) tma3_e(wmbuf + k * 7168, &p.wm, mcol + (k >> 1) * 16, (k & 1) * 224, 0, BAR(B_WMFULL));
                    }
                    bar_sync(9, 384);
                    if (sc) return;
                    mbar_wait(BAR(B_MOD1), 0);
                    mbar_wait(BAR(B_WMFREE), 0);
                }
                if (mt == 2) mbar_wait(BAR(B_XFREE), 0);
                if (mt == 3) mbar_wait(BAR(B_VRFULL), 0);
                const uint32_t bar = BAR(mt == 3 ? B_WOFULL : B_FULLK + mt), dst = sb + (mt < 2 ? OFF_Y : OFF_X) + (mt & 1) * HALF;
                const int c0 = (mt < 2 ? DM + DM * mt : 0) + 56 * j - 8 * kh;
                if (!sc) {
                    expect_e(bar, HALF);
                    tma3_e(dst, mt == 3 ? &p.wo : &p.qkv, c0, 0, 0, bar);
                    tma3_e(dst + HALF / 2, mt == 3 ? &p.wo : &p.qkv, c0, 224, 0, bar);
                }
            }
            expect_e(BAR(B_XCH), 14336);
            expect_e(BAR(B_XCH + 1), 14336);
        } else {
            if (warp == 10 && !sc) l2_prefetch_e((const char*)p.wqkv + (size_t)b * 9408, 9408);
            bar_sync(9, 384);
            if (sc) return;
            target = lds1(sb + M_EPOCH) + 1;
            if (warp == 11) {
                const int col = mcol + (early ? lane & 15 : lane);
                mbar_wait(BAR(B_GEMV), 0);
                float sum = 0.f;
#pragma unroll
                for (int i = 0; i < 8; i++) sum += *(const float*)(smem + OFF_Y + HALF + 29696 + (i * 32 + col - mcol) * 4);
                sum = bf_round(sum);
                if ((col >= DM && col < 2 * DM) || (col >= 4 * DM && col < 5 * DM)) sum += 1.f;
                uint32_t* mg = g_mod + col + (early ? (lane >> 4) * 4 * 6 * DM : 0);
#pragma unroll 1
                for (int i = gemv ? (early ? 4 : 8) : 0; i > 0; i--, mg += 6 * DM) st_relaxed(mg, (pack2(sum, 0.f) << 16) | (target & 0xFFFFu));
                warp_arrive(BAR(B_WMFREE));
            }
            if (warp == 9) {
#pragma unroll 1
                for (int kv = 0; kv < 2; kv++) {
                    mbar_wait(BAR(B_PUB + kv), 0);
                    wait_flags(g_flag + b * 128 + lane, target, (r >= 2 ? 6u : r == 1 ? 2u : 0u) << (8 * kv));
                    fence_async_global();
                    const uint32_t dst = sb + OFF_Y + (kv ? Y_VR : Y_K);
                    expect_e(BAR(B_KRFULL + kv), r >= 2 ? 28672 : r == 1 ? 14336 : 0);
                    if (r >= 2) bulk_e(dst, act - 2 * RB_WORDS + RB_KV + j * 7168 + kv * 3584, 14336, BAR(B_KRFULL + kv));
                    if (r >= 1) bulk_e(dst + 14336, act - RB_WORDS + RB_KV + j * 7168 + kv * 3584, 14336, BAR(B_KRFULL + kv));
                }
            } else if (warp == 11) {
                mbar_wait(BAR(B_VRFULL), 0);
                l2_prefetch_e((const char*)p.wg + (size_t)b * 12544, 12544);
                l2_prefetch_e((const char*)p.wu + (size_t)b * 12544, 12544);
#pragma unroll 1
                for (int k = 0; k < (r < 12 ? 2 : 1); k++) {
                    const int u = 28 * kh + r + 16 * k;
                    expect_e(BAR(B_XFULL + k), 7168);
                    tma3_e(sb + OFF_Y + 102400, &p.dn, 0, 32 * u, 7 * j, BAR(B_XFULL + k));
                    tma3_e(sb + OFF_Y + 102400 + 3584, &p.dn, 0, 32 * u, 7 * (j ^ 1), BAR(B_XFULL + k));
                    mbar_wait(BAR(B_XFULL + k), 1);
                    asm volatile("{\n.reg .pred p;\nelect.sync _|p, 0xffffffff;\n@p cp.async.bulk.global.shared::cta.bulk_group [%0], [%1], 7168;\n"
                                 "cp.async.bulk.commit_group;\ncp.async.bulk.wait_group 0;\n}" ::"l"(g_wd + (size_t)(u * 4 + nq) * 1792), "r"(sb + OFF_Y + 102400) : "memory");
                    __syncwarp();
                }
                warp_arrive(BAR(B_WMFREE));
                fence_gpu();
                if (lane < 16) st_relaxed(g_flag + (8 * lane + j) * 128 + 96 + r, target);
            }
        }
        if (warp == 8 || warp == 11) {
            const int sec = warp == 11;
            if (sec) ring_loader<1>(p, sb, r, j, lane); else ring_loader<0>(p, sb, r, j, lane);
            mbar_wait(BAR(B_DONE), 0);
        } else if (warp == 9) {
#pragma unroll
            for (int ev = 0; ev < 4; ev++) { expect_e(BAR(B_GFULL + ev), ev < 2 ? HALF / 2 : 16384 + 4096); expect_e(BAR(B_XFULL + 2 + ev), ev < 2 ? HALF / 2 : HALF - 16384); }
            mbar_wait(BAR(B_PUB + 2), 0);
            const uint32_t* fp = g_flag + b * 128 + 32 + lane;
            const int par = (target - 1) & 1;
#pragma unroll 1
            for (int n = 0, ev = 0; ev < 4; n++) {
                if (ev == 1) { mbar_wait(BAR(B_WMFREE), 1); mbar_wait(BAR(B_PUB + 3), 0); }
                uint32_t ok = __ballot_sync(~0u, (int)(ld_relaxed(fp) - target) >= 0) >> (8 * ev);
                while ((ok & 0xFFu) == 0xFFu) {
                    asm volatile("fence.acquire.gpu;" ::: "memory");
                    fence_async_global();
                    const int tile = (ev & 1) + (ev >> 1) * par * 2;
                    const uint32_t dst = sb + (ev == 0 ? OFF_X : OFF_Y + (ev & 1) * HALF), first = ev < 2 ? HALF / 2 : 16384;
                    const char* src = (const char*)(act + RB_O + ((ev >> 1) * 2 + tile) * 14336);
                    if (ev >= 2) bulk_e(sb + OFF_X + X_STAT + (ev & 1) * 4096, act + RB_ST + tile * 1024, 4096, BAR(B_GFULL + ev));
                    bulk_e(dst, src, first, BAR(B_GFULL + ev));
                    bulk_e(dst + first, src + first, HALF - first, BAR(B_XFULL + 2 + ev));
                    if (ev) PROFH(4 + ev);
                    ev++; ok >>= 8;
                }
                if (n > SPIN_LIMIT) __trap();
            }
            mbar_wait(BAR(B_XFULL + 5), 1);
#pragma unroll 1
            for (int hf = 0; hf < 2; hf++) {
                const int tile = (par ^ 1) * 2 + hf;
                uint4* xz = (uint4*)(act + RB_X1 + tile * 14336 + j * 1792) + lane;
#pragma unroll
                for (int i = 0; i < 14; i++) xz[i * 32] = make_uint4(0, 0, 0, 0);
                ((uint4*)(act + RB_ST + (tile * 8 + j) * 128))[lane] = make_uint4(0, 0, 0, 0);
            }
#pragma unroll 1
            for (int ps = 0; ps < 3; ps++) {
                mbar_wait(BAR(B_PUB + 6 + ps), 0);
                wait_flags(g_flag + b * 128 + 64 + lane, target, (0x55u << kh) << (8 * ps));
                warp_arrive(BAR(B_HRDY + ps));
                PROFH(9 + ps);
            }
        } else {
#pragma unroll 1
            for (int k = 0; k < 9; k++) {
                uint32_t* fp = k < 2 ? g_flag + (b + 8 * lane) * 128 + k * 8 + lane : g_flag + (8 * r + lane) * 128 + 16 + k * 8 + j;
                mbar_wait(BAR(B_PUB + k), 0);
                if (k != 4 && k != 5) fence_gpu();
                if (k < 2 ? (lane == 1 || lane == 2) : lane < 8) st_relaxed(fp, target);
                if (k >= 3 && k <= 5) PROFH(k - 3);
            }
        }
    }
}

#undef act
typedef CUresult (*EncodeFn)(CUtensorMap*, CUtensorMapDataType, cuuint32_t, void*, const cuuint64_t*, const cuuint64_t*, const cuuint32_t*,
                             const cuuint32_t*, CUtensorMapInterleave, CUtensorMapSwizzle, CUtensorMapL2promotion, CUtensorMapFloatOOBfill);

static void make_map(EncodeFn fn, CUtensorMap* m, const void* ptr, uint64_t d0, uint64_t d1, uint64_t d2, uint64_t s1, uint64_t s2,
                     uint32_t b0, uint32_t b1, uint32_t b2, CUtensorMapSwizzle sw) {
    cuuint64_t dims[3] = {d0, d1, d2}, strides[2] = {s1, s2};
    cuuint32_t box[3] = {b0, b1, b2}, es[3] = {1, 1, 1};
    CUresult rc = fn(m, CU_TENSOR_MAP_DATA_TYPE_BFLOAT16, 3, (void*)ptr, dims, strides, box, es, CU_TENSOR_MAP_INTERLEAVE_NONE, sw,
                     CU_TENSOR_MAP_L2_PROMOTION_L2_128B, CU_TENSOR_MAP_FLOAT_OOB_FILL_NONE);
    (void)rc;
}

extern "C" void kernel_launch(void* const* d_in, const int* in_sizes, int n_in, void* d_out, int out_size) {
    (void)in_sizes; (void)n_in; (void)out_size;
    static EncodeFn fn = nullptr;
    static uint32_t* act_base = nullptr;
    if (!fn) {
        cudaDriverEntryPointQueryResult st;
        cudaGetDriverEntryPoint("cuTensorMapEncodeTiled", (void**)&fn, cudaEnableDefault, &st);
        void* a = nullptr;
        cudaGetSymbolAddress(&a, g_act);
        act_base = (uint32_t*)(((uintptr_t)a + 0xFFFFF) & ~(uintptr_t)0xFFFFF);
        cudaFuncSetAttribute(fused_block_kernel, cudaFuncAttributeMaxDynamicSharedMemorySize, SMEM_BYTES);
    }
    Params p;
    p.x = (const bf16*)d_in[0];
    const bf16* wqkv = (const bf16*)d_in[1];
    p.wqkv = wqkv;
    p.wop = (const bf16*)d_in[2];
    p.wg = (const bf16*)d_in[4];
    p.wu = (const bf16*)d_in[5];
    p.wd = (const bf16*)d_in[6];
    p.c = (const bf16*)d_in[7];
    p.wmod = (const bf16*)d_in[8];
    p.out = (bf16*)d_out;
    p.zero = 0;
    p.actb = act_base;
    make_map(fn, &p.wm, p.wmod, 2688, 448, 1, 5376, 5376 * 448, 16, 224, 1, CU_TENSOR_MAP_SWIZZLE_NONE);
    make_map(fn, &p.xm, p.x, 448, 2048, 1, 896, 896 * 2048, 64, 128, 1, CU_TENSOR_MAP_SWIZZLE_128B);
    make_map(fn, &p.qkv, wqkv, 1344, 448, 1, 2688, 2688 * 448, 64, 224, 1, CU_TENSOR_MAP_SWIZZLE_128B);
    make_map(fn, &p.wo, p.wop, 448, 448, 1, 896, 896 * 448, 64, 224, 1, CU_TENSOR_MAP_SWIZZLE_128B);
    make_map(fn, &p.ga, p.wg, 64, 448, 28, 3584, 128, 64, 32, 2, CU_TENSOR_MAP_SWIZZLE_128B);
    make_map(fn, &p.ua, p.wu, 64, 448, 28, 3584, 128, 64, 32, 2, CU_TENSOR_MAP_SWIZZLE_128B);
    make_map(fn, &p.gb, p.wg, 64, 448, 28, 3584, 128, 64, 64, 1, CU_TENSOR_MAP_SWIZZLE_128B);
    make_map(fn, &p.ub, p.wu, 64, 448, 28, 3584, 128, 64, 64, 1, CU_TENSOR_MAP_SWIZZLE_128B);
    make_map(fn, &p.gc, p.wg, 32, 448, 56, 3584, 64, 32, 64, 1, CU_TENSOR_MAP_SWIZZLE_64B);
    make_map(fn, &p.uc, p.wu, 32, 448, 56, 3584, 64, 32, 64, 1, CU_TENSOR_MAP_SWIZZLE_64B);
    make_map(fn, &p.dn, p.wd, 8, 1792, 56, 896, 16, 8, 32, 7, CU_TENSOR_MAP_SWIZZLE_NONE);
    fused_block_kernel<<<GRID, 384, SMEM_BYTES>>>(p);
}
```

```cpp
#include <cuda_runtime.h>
#include <cuda_bf16.h>
#include <cuda.h>
#include <stdint.h>

typedef __nv_bfloat16 bf16;

template<uint64_t CB> __device__ __forceinline__ void wgmma_rs_56(float* d, uint32_t a0, uint32_t a1, uint32_t a2, uint32_t a3, uint32_t db, int sd) {
  asm volatile("{\n.reg .pred p;\n.reg .b64 b;\nsetp.ne.b32 p, %33, 0;\nmov.b64 b, {%32, %34};\n"
    "wgmma.mma_async.sync.aligned.m64n56k16.f32.bf16.bf16 {%0,%1,%2,%3,%4,%5,%6,%7,%8,%9,%10,%11,%12,%13,%14,%15,%16,%17,%18,%19,%20,%21,%22,%23,%24,%25,%26,%27}, {%28,%29,%30,%31}, b, p, 1, 1, 1;\n}\n"
    : "+f"(d[0]),"+f"(d[1]),"+f"(d[2]),"+f"(d[3]),"+f"(d[4]),"+f"(d[5]),"+f"(d[6]),"+f"(d[7]),"+f"(d[8]),"+f"(d[9]),"+f"(d[10]),"+f"(d[11]),"+f"(d[12]),"+f"(d[13]),"+f"(d[14]),"+f"(d[15]),"+f"(d[16]),"+f"(d[17]),"+f"(d[18]),"+f"(d[19]),"+f"(d[20]),"+f"(d[21]),"+f"(d[22]),"+f"(d[23]),"+f"(d[24]),"+f"(d[25]),"+f"(d[26]),"+f"(d[27])
    : "r"(a0), "r"(a1), "r"(a2), "r"(a3), "r"(db), "r"(sd), "n"((uint32_t)(CB >> 32)));
}
template<uint64_t CA, uint64_t CB> __device__ __forceinline__ void wgmma_ss_56(float* d, uint32_t da, uint32_t db, int sd) {
  asm volatile("{\n.reg .pred p;\n.reg .b64 a, b;\nsetp.ne.b32 p, %30, 0;\nmov.b64 a, {%28, %31};\nmov.b64 b, {%29, %32};\n"
    "wgmma.mma_async.sync.aligned.m64n56k16.f32.bf16.bf16 {%0,%1,%2,%3,%4,%5,%6,%7,%8,%9,%10,%11,%12,%13,%14,%15,%16,%17,%18,%19,%20,%21,%22,%23,%24,%25,%26,%27}, a, b, p, 1, 1, 0, 1;\n}\n"
    : "+f"(d[0]),"+f"(d[1]),"+f"(d[2]),"+f"(d[3]),"+f"(d[4]),"+f"(d[5]),"+f"(d[6]),"+f"(d[7]),"+f"(d[8]),"+f"(d[9]),"+f"(d[10]),"+f"(d[11]),"+f"(d[12]),"+f"(d[13]),"+f"(d[14]),"+f"(d[15]),"+f"(d[16]),"+f"(d[17]),"+f"(d[18]),"+f"(d[19]),"+f"(d[20]),"+f"(d[21]),"+f"(d[22]),"+f"(d[23]),"+f"(d[24]),"+f"(d[25]),"+f"(d[26]),"+f"(d[27])
    : "r"(da), "r"(db), "r"(sd), "n"((uint32_t)(CA >> 32)), "n"((uint32_t)(CB >> 32)));
}
template<uint64_t CB> __device__ __forceinline__ void wgmma_rs_256(float* d, uint32_t a0, uint32_t a1, uint32_t a2, uint32_t a3, uint32_t db, int sd) {
  asm volatile("{\n.reg .pred p;\n.reg .b64 b;\nsetp.ne.b32 p, %133, 0;\nmov.b64 b, {%132, %134};\n"
    "wgmma.mma_async.sync.aligned.m64n256k16.f32.bf16.bf16 {%0,%1,%2,%3,%4,%5,%6,%7,%8,%9,%10,%11,%12,%13,%14,%15,%16,%17,%18,%19,%20,%21,%22,%23,%24,%25,%26,%27,%28,%29,%30,%31,%32,%33,%34,%35,%36,%37,%38,%39,%40,%41,%42,%43,%44,%45,%46,%47,%48,%49,%50,%51,%52,%53,%54,%55,%56,%57,%58,%59,%60,%61,%62,%63,%64,%65,%66,%67,%68,%69,%70,%71,%72,%73,%74,%75,%76,%77,%78,%79,%80,%81,%82,%83,%84,%85,%86,%87,%88,%89,%90,%91,%92,%93,%94,%95,%96,%97,%98,%99,%100,%101,%102,%103,%104,%105,%106,%107,%108,%109,%110,%111,%112,%113,%114,%115,%116,%117,%118,%119,%120,%121,%122,%123,%124,%125,%126,%127}, {%128,%129,%130,%131}, b, p, 1, 1, 1;\n}\n"
    : "+f"(d[0]),"+f"(d[1]),"+f"(d[2]),"+f"(d[3]),"+f"(d[4]),"+f"(d[5]),"+f"(d[6]),"+f"(d[7]),"+f"(d[8]),"+f"(d[9]),"+f"(d[10]),"+f"(d[11]),"+f"(d[12]),"+f"(d[13]),"+f"(d[14]),"+f"(d[15]),"+f"(d[16]),"+f"(d[17]),"+f"(d[18]),"+f"(d[19]),"+f"(d[20]),"+f"(d[21]),"+f"(d[22]),"+f"(d[23]),"+f"(d[24]),"+f"(d[25]),"+f"(d[26]),"+f"(d[27]),"+f"(d[28]),"+f"(d[29]),"+f"(d[30]),"+f"(d[31]),"+f"(d[32]),"+f"(d[33]),"+f"(d[34]),"+f"(d[35]),"+f"(d[36]),"+f"(d[37]),"+f"(d[38]),"+f"(d[39]),"+f"(d[40]),"+f"(d[41]),"+f"(d[42]),"+f"(d[43]),"+f"(d[44]),"+f"(d[45]),"+f"(d[46]),"+f"(d[47]),"+f"(d[48]),"+f"(d[49]),"+f"(d[50]),"+f"(d[51]),"+f"(d[52]),"+f"(d[53]),"+f"(d[54]),"+f"(d[55]),"+f"(d[56]),"+f"(d[57]),"+f"(d[58]),"+f"(d[59]),"+f"(d[60]),"+f"(d[61]),"+f"(d[62]),"+f"(d[63]),"+f"(d[64]),"+f"(d[65]),"+f"(d[66]),"+f"(d[67]),"+f"(d[68]),"+f"(d[69]),"+f"(d[70]),"+f"(d[71]),"+f"(d[72]),"+f"(d[73]),"+f"(d[74]),"+f"(d[75]),"+f"(d[76]),"+f"(d[77]),"+f"(d[78]),"+f"(d[79]),"+f"(d[80]),"+f"(d[81]),"+f"(d[82]),"+f"(d[83]),"+f"(d[84]),"+f"(d[85]),"+f"(d[86]),"+f"(d[87]),"+f"(d[88]),"+f"(d[89]),"+f"(d[90]),"+f"(d[91]),"+f"(d[92]),"+f"(d[93]),"+f"(d[94]),"+f"(d[95]),"+f"(d[96]),"+f"(d[97]),"+f"(d[98]),"+f"(d[99]),"+f"(d[100]),"+f"(d[101]),"+f"(d[102]),"+f"(d[103]),"+f"(d[104]),"+f"(d[105]),"+f"(d[106]),"+f"(d[107]),"+f"(d[108]),"+f"(d[109]),"+f"(d[110]),"+f"(d[111]),"+f"(d[112]),"+f"(d[113]),"+f"(d[114]),"+f"(d[115]),"+f"(d[116]),"+f"(d[117]),"+f"(d[118]),"+f"(d[119]),"+f"(d[120]),"+f"(d[121]),"+f"(d[122]),"+f"(d[123]),"+f"(d[124]),"+f"(d[125]),"+f"(d[126]),"+f"(d[127])
    : "r"(a0), "r"(a1), "r"(a2), "r"(a3), "r"(db), "r"(sd), "n"((uint32_t)(CB >> 32)));
}
template<uint64_t CA, uint64_t CB> __device__ __forceinline__ void wgmma_ss_128(float* d, uint32_t da, uint32_t db, int sd) {
  asm volatile("{\n.reg .pred p;\n.reg .b64 a, b;\nsetp.ne.b32 p, %66, 0;\nmov.b64 a, {%64, %67};\nmov.b64 b, {%65, %68};\n"
    "wgmma.mma_async.sync.aligned.m64n128k16.f32.bf16.bf16 {%0,%1,%2,%3,%4,%5,%6,%7,%8,%9,%10,%11,%12,%13,%14,%15,%16,%17,%18,%19,%20,%21,%22,%23,%24,%25,%26,%27,%28,%29,%30,%31,%32,%33,%34,%35,%36,%37,%38,%39,%40,%41,%42,%43,%44,%45,%46,%47,%48,%49,%50,%51,%52,%53,%54,%55,%56,%57,%58,%59,%60,%61,%62,%63}, a, b, p, 1, 1, 0, 1;\n}\n"
    : "+f"(d[0]),"+f"(d[1]),"+f"(d[2]),"+f"(d[3]),"+f"(d[4]),"+f"(d[5]),"+f"(d[6]),"+f"(d[7]),"+f"(d[8]),"+f"(d[9]),"+f"(d[10]),"+f"(d[11]),"+f"(d[12]),"+f"(d[13]),"+f"(d[14]),"+f"(d[15]),"+f"(d[16]),"+f"(d[17]),"+f"(d[18]),"+f"(d[19]),"+f"(d[20]),"+f"(d[21]),"+f"(d[22]),"+f"(d[23]),"+f"(d[24]),"+f"(d[25]),"+f"(d[26]),"+f"(d[27]),"+f"(d[28]),"+f"(d[29]),"+f"(d[30]),"+f"(d[31]),"+f"(d[32]),"+f"(d[33]),"+f"(d[34]),"+f"(d[35]),"+f"(d[36]),"+f"(d[37]),"+f"(d[38]),"+f"(d[39]),"+f"(d[40]),"+f"(d[41]),"+f"(d[42]),"+f"(d[43]),"+f"(d[44]),"+f"(d[45]),"+f"(d[46]),"+f"(d[47]),"+f"(d[48]),"+f"(d[49]),"+f"(d[50]),"+f"(d[51]),"+f"(d[52]),"+f"(d[53]),"+f"(d[54]),"+f"(d[55]),"+f"(d[56]),"+f"(d[57]),"+f"(d[58]),"+f"(d[59]),"+f"(d[60]),"+f"(d[61]),"+f"(d[62]),"+f"(d[63])
    : "r"(da), "r"(db), "r"(sd), "n"((uint32_t)(CA >> 32)), "n"((uint32_t)(CB >> 32)));
}
template<uint64_t CA, uint64_t CB> __device__ __forceinline__ void wgmma_ss_64(float* d, uint32_t da, uint32_t db, int sd) {
  asm volatile("{\n.reg .pred p;\n.reg .b64 a, b;\nsetp.ne.b32 p, %34, 0;\nmov.b64 a, {%32, %35};\nmov.b64 b, {%33, %36};\n"
    "wgmma.mma_async.sync.aligned.m64n64k16.f32.bf16.bf16 {%0,%1,%2,%3,%4,%5,%6,%7,%8,%9,%10,%11,%12,%13,%14,%15,%16,%17,%18,%19,%20,%21,%22,%23,%24,%25,%26,%27,%28,%29,%30,%31}, a, b, p, 1, 1, 0, 1;\n}\n"
    : "+f"(d[0]),"+f"(d[1]),"+f"(d[2]),"+f"(d[3]),"+f"(d[4]),"+f"(d[5]),"+f"(d[6]),"+f"(d[7]),"+f"(d[8]),"+f"(d[9]),"+f"(d[10]),"+f"(d[11]),"+f"(d[12]),"+f"(d[13]),"+f"(d[14]),"+f"(d[15]),"+f"(d[16]),"+f"(d[17]),"+f"(d[18]),"+f"(d[19]),"+f"(d[20]),"+f"(d[21]),"+f"(d[22]),"+f"(d[23]),"+f"(d[24]),"+f"(d[25]),"+f"(d[26]),"+f"(d[27]),"+f"(d[28]),"+f"(d[29]),"+f"(d[30]),"+f"(d[31])
    : "r"(da), "r"(db), "r"(sd), "n"((uint32_t)(CA >> 32)), "n"((uint32_t)(CB >> 32)));
}
template<uint64_t CA, uint64_t CB> __device__ __forceinline__ void wgmma_ss_112(float* d, uint32_t da, uint32_t db, int sd) {
  asm volatile("{\n.reg .pred p;\n.reg .b64 a, b;\nsetp.ne.b32 p, %58, 0;\nmov.b64 a, {%56, %59};\nmov.b64 b, {%57, %60};\n"
    "wgmma.mma_async.sync.aligned.m64n112k16.f32.bf16.bf16 {%0,%1,%2,%3,%4,%5,%6,%7,%8,%9,%10,%11,%12,%13,%14,%15,%16,%17,%18,%19,%20,%21,%22,%23,%24,%25,%26,%27,%28,%29,%30,%31,%32,%33,%34,%35,%36,%37,%38,%39,%40,%41,%42,%43,%44,%45,%46,%47,%48,%49,%50,%51,%52,%53,%54,%55}, a, b, p, 1, 1, 0, 1;\n}\n"
    : "+f"(d[0]),"+f"(d[1]),"+f"(d[2]),"+f"(d[3]),"+f"(d[4]),"+f"(d[5]),"+f"(d[6]),"+f"(d[7]),"+f"(d[8]),"+f"(d[9]),"+f"(d[10]),"+f"(d[11]),"+f"(d[12]),"+f"(d[13]),"+f"(d[14]),"+f"(d[15]),"+f"(d[16]),"+f"(d[17]),"+f"(d[18]),"+f"(d[19]),"+f"(d[20]),"+f"(d[21]),"+f"(d[22]),"+f"(d[23]),"+f"(d[24]),"+f"(d[25]),"+f"(d[26]),"+f"(d[27]),"+f"(d[28]),"+f"(d[29]),"+f"(d[30]),"+f"(d[31]),"+f"(d[32]),"+f"(d[33]),"+f"(d[34]),"+f"(d[35]),"+f"(d[36]),"+f"(d[37]),"+f"(d[38]),"+f"(d[39]),"+f"(d[40]),"+f"(d[41]),"+f"(d[42]),"+f"(d[43]),"+f"(d[44]),"+f"(d[45]),"+f"(d[46]),"+f"(d[47]),"+f"(d[48]),"+f"(d[49]),"+f"(d[50]),"+f"(d[51]),"+f"(d[52]),"+f"(d[53]),"+f"(d[54]),"+f"(d[55])
    : "r"(da), "r"(db), "r"(sd), "n"((uint32_t)(CA >> 32)), "n"((uint32_t)(CB >> 32)));
}
template<uint64_t CB> __device__ __forceinline__ void wgmma_rs_112(float* d, uint32_t a0, uint32_t a1, uint32_t a2, uint32_t a3, uint32_t db, int sd) {
  asm volatile("{\n.reg .pred p;\n.reg .b64 b;\nsetp.ne.b32 p, %61, 0;\nmov.b64 b, {%60, %62};\n"
    "wgmma.mma_async.sync.aligned.m64n112k16.f32.bf16.bf16 {%0,%1,%2,%3,%4,%5,%6,%7,%8,%9,%10,%11,%12,%13,%14,%15,%16,%17,%18,%19,%20,%21,%22,%23,%24,%25,%26,%27,%28,%29,%30,%31,%32,%33,%34,%35,%36,%37,%38,%39,%40,%41,%42,%43,%44,%45,%46,%47,%48,%49,%50,%51,%52,%53,%54,%55}, {%56,%57,%58,%59}, b, p, 1, 1, 1;\n}\n"
    : "+f"(d[0]),"+f"(d[1]),"+f"(d[2]),"+f"(d[3]),"+f"(d[4]),"+f"(d[5]),"+f"(d[6]),"+f"(d[7]),"+f"(d[8]),"+f"(d[9]),"+f"(d[10]),"+f"(d[11]),"+f"(d[12]),"+f"(d[13]),"+f"(d[14]),"+f"(d[15]),"+f"(d[16]),"+f"(d[17]),"+f"(d[18]),"+f"(d[19]),"+f"(d[20]),"+f"(d[21]),"+f"(d[22]),"+f"(d[23]),"+f"(d[24]),"+f"(d[25]),"+f"(d[26]),"+f"(d[27]),"+f"(d[28]),"+f"(d[29]),"+f"(d[30]),"+f"(d[31]),"+f"(d[32]),"+f"(d[33]),"+f"(d[34]),"+f"(d[35]),"+f"(d[36]),"+f"(d[37]),"+f"(d[38]),"+f"(d[39]),"+f"(d[40]),"+f"(d[41]),"+f"(d[42]),"+f"(d[43]),"+f"(d[44]),"+f"(d[45]),"+f"(d[46]),"+f"(d[47]),"+f"(d[48]),"+f"(d[49]),"+f"(d[50]),"+f"(d[51]),"+f"(d[52]),"+f"(d[53]),"+f"(d[54]),"+f"(d[55])
    : "r"(a0), "r"(a1), "r"(a2), "r"(a3), "r"(db), "r"(sd), "n"((uint32_t)(CB >> 32)));
}

constexpr int DM = 448;
constexpr int NCTA = 128;
#define MAPPING 1
#define GRID 132
#define PINGPONG 0
#define WIN 6
#define WIN_END 25
#define UNR_B 1
#define UNR_C 1
constexpr int kB = UNR_B, kC = UNR_C;
#define MAP_S 4
constexpr int SPIN_LIMIT = 1 << 22;

constexpr uint32_t OFF_X = 0, OFF_Y = 114688, OFF_MISC = 229376, SMEM_BYTES = 232448;
constexpr uint32_t Y_VR = 0, Y_K = 28672, Y_KOWN = 57344, Y_VOWN = 71680, Y_Q = 86016;
constexpr uint32_t HALF = 57344;
constexpr uint32_t X_STAT = 49152;
constexpr uint32_t M_BAR = OFF_MISC;
constexpr uint32_t M_ST = OFF_MISC + 512;
constexpr uint32_t M_G = OFF_MISC + 2304;
constexpr uint32_t M_EPOCH = OFF_MISC + 3040;
enum { B_XFULL = 0, B_FULLK = 7, B_FULLV = 8, B_FULLQ, B_KRFULL, B_VRFULL, B_WOFULL, B_XCH, B_MOD1 = 15, B_FULL = 16, B_WMFULL = 30,
       B_EMPTY = 32, B_XFREE = B_EMPTY + 12, B_GEMV, B_PEER,
       B_PUB = 47,
       B_WMFREE = 56, B_HRDY, B_GFULL = B_HRDY + 3, B_DONE = 31, B_DUMMY = B_GEMV };

__device__ uint32_t g_ticket;
__device__ __align__(128) uint32_t g_mod[8 * 6 * DM];
__device__ __align__(128) uint32_t g_flag[144 * 128];
constexpr int RB_WORDS = 262144, RB_KV = 0, RB_O = 57344, RB_X1 = 86016, RB_H2 = 143360, RB_ST = 258048;
__device__ __align__(128) uint32_t g_act[18 * RB_WORDS];
__device__ __align__(128) uint32_t g_wd[56 * 4 * 1792];
#define PROFH(id)
#define PROFH1(id)
#define PROFC(id)

struct alignas(64) Params {
    CUtensorMap wm, xm, qkv, wo, ga, ua, gb, ub, gc, uc, dn;
    const bf16 *x, *c, *wqkv, *wmod, *wg, *wu, *wd, *wop;
    bf16* out;
    uint32_t* actb;
    uint32_t zero;
};

__device__ __forceinline__ void mbar_init(uint32_t bar, int cnt) { asm volatile("mbarrier.init.shared::cta.b64 [%0], %1;" ::"r"(bar), "r"(cnt) : "memory"); }
__device__ __forceinline__ void mbar_expect_tx(uint32_t bar, uint32_t bytes) { asm volatile("mbarrier.arrive.expect_tx.shared::cta.b64 _, [%0], %1;" ::"r"(bar), "r"(bytes) : "memory"); }
__device__ __forceinline__ void mbar_arrive(uint32_t bar) { asm volatile("mbarrier.arrive.shared::cta.b64 _, [%0];" ::"r"(bar) : "memory"); }
__device__ __forceinline__ void mbar_wait(uint32_t bar, uint32_t parity) {
    uint32_t ok; int n = 0;
    do {
        asm volatile("{\n.reg .pred p;\nmbarrier.try_wait.parity.shared::cta.b64 p, [%1], %2;\nselp.u32 %0, 1, 0, p;\n}" : "=r"(ok) : "r"(bar), "r"(parity) : "memory");
        if (++n > SPIN_LIMIT) __trap();
    } while (!ok);
}
__device__ __forceinline__ void mbar_wait_c(uint32_t bar, uint32_t parity) {
    asm volatile("{\n.reg .pred p;\nWL:\nmbarrier.try_wait.parity.shared::cta.b64 p, [%0], %1;\n@!p bra WL;\n}" ::"r"(bar), "r"(parity) : "memory");
}
__device__ __forceinline__ void mbar_wait_cluster(uint32_t bar, uint32_t parity) {
    uint32_t ok; int n = 0;
    do {
        asm volatile("{\n.reg .pred p;\nmbarrier.try_wait.parity.acquire.cluster.shared::cta.b64 p, [%1], %2;\nselp.u32 %0, 1, 0, p;\n}" : "=r"(ok) : "r"(bar), "r"(parity) : "memory");
        if (++n > SPIN_LIMIT) __trap();
    } while (!ok);
}
__device__ __forceinline__ void warp_arrive(uint32_t bar) {
    __syncwarp();
    asm volatile("{\n.reg .pred p;\nelect.sync _|p, 0xffffffff;\n@p mbarrier.arrive.shared::cta.b64 _, [%0];\n}" ::"r"(bar) : "memory");
}
__device__ __forceinline__ int opaque(int v) { return __shfl_sync(~0u, v, 0); }
__device__ __forceinline__ int fresh_tid() { int v; asm volatile("mov.u32 %0, %%tid.x;" : "=r"(v)); return v; }
__device__ __forceinline__ void bar_sync(int id, int n) { asm volatile("bar.sync %0, %1;" ::"r"(id), "r"(n) : "memory"); }
__device__ __forceinline__ void bar_arrive(int id, int n) { asm volatile("bar.arrive %0, %1;" ::"r"(id), "r"(n) : "memory"); }
__device__ __forceinline__ void fence_async_smem() { asm volatile("fence.proxy.async.shared::cta;" ::: "memory"); }
__device__ __forceinline__ void fence_async_global() { asm volatile("fence.proxy.async.global;" ::: "memory"); }
__device__ __forceinline__ void fence_gpu() { asm volatile("fence.release.gpu;" ::: "memory"); }
__device__ __forceinline__ void tma3(uint32_t dst, const CUtensorMap* m, int c0, int c1, int c2, uint32_t bar) {
    asm volatile("cp.async.bulk.tensor.3d.shared::cluster.global.mbarrier::complete_tx::bytes [%0], [%1, {%3, %4, %5}], [%2];"
                 ::"r"(dst), "l"(m), "r"(bar), "r"(c0), "r"(c1), "r"(c2) : "memory");
}
__device__ __forceinline__ void bulk_load(uint32_t dst, const void* src, uint32_t bytes, uint32_t bar) {
    asm volatile("cp.async.bulk.shared::cluster.global.mbarrier::complete_tx::bytes [%0], [%1], %2, [%3];" ::"r"(dst), "l"(src), "r"(bytes), "r"(bar) : "memory");
}
__device__ __forceinline__ void expect_e(uint32_t bar, uint32_t bytes) {
    asm volatile("{\n.reg .pred p;\nelect.sync _|p, 0xffffffff;\n@p mbarrier.arrive.expect_tx.shared::cta.b64 _, [%0], %1;\n}" ::"r"(bar), "r"(bytes) : "memory");
}
__device__ __forceinline__ void tma3_e(uint32_t dst, const CUtensorMap* m, int c0, int c1, int c2, uint32_t bar) {
    asm volatile("{\n.reg .pred p;\nelect.sync _|p, 0xffffffff;\n@p cp.async.bulk.tensor.3d.shared::cluster.global.mbarrier::complete_tx::bytes [%0], [%1, {%3, %4, %5}], [%2];\n}"
                 ::"r"(dst), "l"(m), "r"(bar), "r"(c0), "r"(c1), "r"(c2) : "memory");
}
__device__ __forceinline__ void bulk_e(uint32_t dst, const void* src, uint32_t bytes, uint32_t bar) {
    asm volatile("{\n.reg .pred p;\nelect.sync _|p, 0xffffffff;\n@p cp.async.bulk.shared::cluster.global.mbarrier::complete_tx::bytes [%0], [%1], %2, [%3];\n}"
                 ::"r"(dst), "l"(src), "r"(bytes), "r"(bar) : "memory");
}
__device__ __forceinline__ void init_e(uint32_t bar, int cnt) {
    asm volatile("{\n.reg .pred p;\nelect.sync _|p, 0xffffffff;\n@p mbarrier.init.shared::cta.b64 [%0], %1;\n}" ::"r"(bar), "r"(cnt) : "memory");
}
__device__ __forceinline__ void l2_prefetch_e(const void* src, uint32_t bytes) {
    asm volatile("{\n.reg .pred p;\nelect.sync _|p, 0xffffffff;\n@p cp.async.bulk.prefetch.L2.global [%0], %1;\n}" ::"l"(src), "r"(bytes) : "memory");
}
__device__ __forceinline__ uint32_t ld_relaxed(const uint32_t* p) { uint32_t v; asm volatile("ld.relaxed.gpu.global.u32 %0, [%1];" : "=r"(v) : "l"(p) : "memory"); return v; }
__device__ __forceinline__ void st_relaxed(uint32_t* p, uint32_t v) { asm volatile("st.relaxed.gpu.global.u32 [%0], %1;" ::"l"(p), "r"(v) : "memory"); }
__device__ __forceinline__ uint4 ld_relaxed4(const uint4* p) { uint4 v; asm volatile("ld.relaxed.gpu.global.v4.u32 {%0,%1,%2,%3}, [%4];" : "=r"(v.x), "=r"(v.y), "=r"(v.z), "=r"(v.w) : "l"(p) : "memory"); return v; }
__device__ __forceinline__ void st_relaxed4(uint4* p, uint4 v) { asm volatile("st.relaxed.gpu.global.v4.u32 [%0], {%1,%2,%3,%4};" ::"l"(p), "r"(v.x), "r"(v.y), "r"(v.z), "r"(v.w) : "memory"); }
__device__ __forceinline__ uint4 ldg_nc4(const void* p) { uint4 v; asm volatile("ld.global.nc.L1::no_allocate.v4.u32 {%0,%1,%2,%3}, [%4];" : "=r"(v.x), "=r"(v.y), "=r"(v.z), "=r"(v.w) : "l"(p)); return v; }
__device__ __forceinline__ uint32_t ldg_nc(const void* p) { uint32_t v; asm volatile("ld.global.nc.u32 %0, [%1];" : "=r"(v) : "l"(p)); return v; }
__device__ __forceinline__ uint32_t ld_acquire(const uint32_t* p) { uint32_t v; asm volatile("ld.acquire.gpu.global.u32 %0, [%1];" : "=r"(v) : "l"(p) : "memory"); return v; }
__device__ __forceinline__ uint4 lds4(uint32_t a) { uint4 v; asm volatile("ld.shared.v4.u32 {%0,%1,%2,%3}, [%4];" : "=r"(v.x), "=r"(v.y), "=r"(v.z), "=r"(v.w) : "r"(a) : "memory"); return v; }
__device__ __forceinline__ float2 lds2f(uint32_t a) { float2 v; asm volatile("ld.shared.v2.f32 {%0,%1}, [%2];" : "=f"(v.x), "=f"(v.y) : "r"(a) : "memory"); return v; }
__device__ __forceinline__ uint32_t lds1(uint32_t a) { uint32_t v; asm volatile("ld.shared.u32 %0, [%1];" : "=r"(v) : "r"(a) : "memory"); return v; }
__device__ __forceinline__ void sts4(uint32_t a, uint4 v) { asm volatile("st.shared.v4.u32 [%0], {%1,%2,%3,%4};" ::"r"(a), "r"(v.x), "r"(v.y), "r"(v.z), "r"(v.w) : "memory"); }
__device__ __forceinline__ void sts2(uint32_t a, uint32_t x, uint32_t y) { asm volatile("st.shared.v2.u32 [%0], {%1,%2};" ::"r"(a), "r"(x), "r"(y) : "memory"); }
__device__ __forceinline__ void sts1(uint32_t a, uint32_t v) { asm volatile("st.shared.u32 [%0], %1;" ::"r"(a), "r"(v) : "memory"); }
__device__ __forceinline__ void stsm4(uint32_t a, uint32_t r0, uint32_t r1, uint32_t r2, uint32_t r3) {
    asm volatile("stmatrix.sync.aligned.m8n8.x4.shared.b16 [%0], {%1,%2,%3,%4};" ::"r"(a), "r"(r0), "r"(r1), "r"(r2), "r"(r3));
}
__device__ __forceinline__ uint32_t pack2(float lo, float hi) { uint32_t r; asm("cvt.rn.bf16x2.f32 %0, %1, %2;" : "=r"(r) : "f"(hi), "f"(lo)); return r; }
__device__ __forceinline__ uint32_t pack2_relu(float lo, float hi) { uint32_t r; asm("cvt.rn.relu.bf16x2.f32 %0, %1, %2;" : "=r"(r) : "f"(hi), "f"(lo)); return r; }
__device__ __forceinline__ uint32_t hfma2(uint32_t a, uint32_t b, uint32_t c) { uint32_t r; asm("fma.rn.bf16x2 %0, %1, %2, %3;" : "=r"(r) : "r"(a), "r"(b), "r"(c)); return r; }
__device__ __forceinline__ uint32_t hmul2(uint32_t a, uint32_t b) { uint32_t r; asm("mul.rn.bf16x2 %0, %1, %2;" : "=r"(r) : "r"(a), "r"(b)); return r; }
__device__ __forceinline__ float bf_lo(uint32_t v) { return __uint_as_float(v << 16); }
__device__ __forceinline__ float bf_hi(uint32_t v) { return __uint_as_float(v & 0xFFFF0000u); }
__device__ __forceinline__ float bf_round(float v) { return bf_lo(pack2(v, 0.f)); }
__device__ __forceinline__ float ex2(float x) { float r; asm("ex2.approx.ftz.f32 %0, %1;" : "=f"(r) : "f"(x)); return r; }
__device__ __forceinline__ void mma16816(float* d, uint32_t a0, uint32_t a1, uint32_t a2, uint32_t a3, uint32_t b0, uint32_t b1) {
    asm("mma.sync.aligned.m16n8k16.row.col.f32.bf16.bf16.f32 {%0,%1,%2,%3}, {%4,%5,%6,%7}, {%8,%9}, {%0,%1,%2,%3};"
        : "+f"(d[0]), "+f"(d[1]), "+f"(d[2]), "+f"(d[3]) : "r"(a0), "r"(a1), "r"(a2), "r"(a3), "r"(b0), "r"(b1));
}
__device__ __forceinline__ void mma16816_first(float* d, uint32_t a0, uint32_t a1, uint32_t a2, uint32_t a3, uint32_t b0, uint32_t b1) {
    asm volatile("mma.sync.aligned.m16n8k16.row.col.f32.bf16.bf16.f32 {%0,%1,%2,%3}, {%4,%5,%6,%7}, {%8,%9}, {%10,%10,%10,%10};"
        : "=f"(d[0]), "=f"(d[1]), "=f"(d[2]), "=f"(d[3]) : "r"(a0), "r"(a1), "r"(a2), "r"(a3), "r"(b0), "r"(b1), "f"(0.f));
}
__device__ __forceinline__ void mma16816_v(float* d, uint32_t a0, uint32_t a1, uint32_t a2, uint32_t a3, uint32_t b0, uint32_t b1) {
    asm volatile("mma.sync.aligned.m16n8k16.row.col.f32.bf16.bf16.f32 {%0,%1,%2,%3}, {%4,%5,%6,%7}, {%8,%9}, {%0,%1,%2,%3};"
        : "+f"(d[0]), "+f"(d[1]), "+f"(d[2]), "+f"(d[3]) : "r"(a0), "r"(a1), "r"(a2), "r"(a3), "r"(b0), "r"(b1));
}
__device__ __forceinline__ void mma1688(float* d, uint32_t a0, uint32_t a1, uint32_t b0) {
    asm("mma.sync.aligned.m16n8k8.row.col.f32.bf16.bf16.f32 {%0,%1,%2,%3}, {%4,%5}, {%6}, {%0,%1,%2,%3};"
        : "+f"(d[0]), "+f"(d[1]), "+f"(d[2]), "+f"(d[3]) : "r"(a0), "r"(a1), "r"(b0));
}
__device__ __forceinline__ void ldsm4(uint32_t a, uint32_t* r) {
    asm volatile("ldmatrix.sync.aligned.m8n8.x4.shared.b16 {%0,%1,%2,%3}, [%4];" : "=r"(r[0]), "=r"(r[1]), "=r"(r[2]), "=r"(r[3]) : "r"(a));
}
__device__ __forceinline__ void ldsm4t(uint32_t a, uint32_t* r) {
    asm volatile("ldmatrix.sync.aligned.m8n8.x4.trans.shared.b16 {%0,%1,%2,%3}, [%4];" : "=r"(r[0]), "=r"(r[1]), "=r"(r[2]), "=r"(r[3]) : "r"(a));
}
__device__ __forceinline__ float rcp(float x) { float r; asm("rcp.approx.ftz.f32 %0, %1;" : "=f"(r) : "f"(x)); return r; }
__device__ __forceinline__ uint2 ld_relaxed2(const void* p) { uint2 v; asm volatile("ld.relaxed.gpu.global.v2.u32 {%0,%1}, [%2];" : "=r"(v.x), "=r"(v.y) : "l"(p) : "memory"); return v; }
__device__ __forceinline__ void st_relaxed2(void* p, uint32_t x, uint32_t y) { asm volatile("st.relaxed.gpu.global.v2.u32 [%0], {%1,%2};" ::"l"(p), "r"(max(x, 1u)), "r"(max(y, 1u)) : "memory"); }
__host__ __device__ constexpr uint64_t dconst(uint32_t lbo, uint32_t sbo, uint32_t swz) {
    return ((uint64_t)(lbo >> 4) << 16) | ((uint64_t)(sbo >> 4) << 32) | ((uint64_t)swz << 62);
}
__device__ __forceinline__ uint32_t mkdesc(uint32_t addr, uint64_t c) { return (uint32_t)c | ((addr & 0x3FFFF) >> 4); }
#define WG_FENCE() asm volatile("wgmma.fence.sync.aligned;" ::: "memory")
#define WG_COMMIT() asm volatile("wgmma.commit_group.sync.aligned;" ::: "memory")
#define WG_WAIT(n) asm volatile("wgmma.wait_group.sync.aligned %0;" ::"n"(n) : "memory")
template <int N> __device__ __forceinline__ void reg_fence(float* d) {
#pragma unroll
    for (int i = 0; i < N; i++) asm volatile("" : "+f"(d[i])::"memory");
}
template <int N> __device__ __forceinline__ void reg_def(float* d) {
#pragma unroll
    for (int i = 0; i < N; i++) asm volatile("" : "=f"(d[i]));
}
template <int N> __device__ __forceinline__ void reg_def(uint32_t* d) {
#pragma unroll
    for (int i = 0; i < N; i++) asm volatile("" : "=r"(d[i]));
}
__device__ __forceinline__ bool is_unset(uint4 v) { return min(min(v.x, v.y), min(v.z, v.w)) == 0u; }
__device__ __forceinline__ uint4 nz4(uint32_t a, uint32_t b, uint32_t c, uint32_t d) { return make_uint4(max(a, 1u), max(b, 1u), max(c, 1u), max(d, 1u)); }
__device__ __forceinline__ void wait_flags(const uint32_t* p, uint32_t target, uint32_t mask) {
    int n = 0;
    while (~__ballot_sync(~0u, (int)(ld_relaxed(p) - target) >= 0) & mask) { if (++n > SPIN_LIMIT) __trap(); }
    asm volatile("fence.acquire.gpu;" ::: "memory");
}
__device__ __forceinline__ float silu_bf(uint32_t cbits) {
    const float c = __uint_as_float(cbits << 16);
    return bf_round(__fdividef(c, 1.f + fminf(ex2(-1.4426950408889634f * c), 1e30f)));
}
__device__ __forceinline__ void gemv_part(uint32_t wmbuf, int npanel, int wp, int lane) {
    const uint32_t wa = wmbuf + wp * 512 + (8 * (lane >> 4) + (lane & 7)) * 32 + ((lane >> 3) & 1) * 16;
    uint2 B[4];
#pragma unroll
    for (int i = 0; i < 4; i++) { const float2 v = lds2f(wmbuf + 28672 + (wp + 8 * i) * 32 + (lane & 3) * 8); B[i] = make_uint2(__float_as_uint(v.x), __float_as_uint(v.y)); }
#pragma unroll 1
    for (int pn = 0; pn < npanel; pn++) {
        float d[4] = {};
        uint32_t A[16];
#pragma unroll
        for (int i = 0; i < 4; i++) ldsm4t(wa + pn * 14336 + (i < 3 || wp < 4 ? i : 0) * 4096, A + 4 * i);
#pragma unroll
        for (int i = 0; i < 4; i++) mma16816(d, A[4 * i], A[4 * i + 1], A[4 * i + 2], A[4 * i + 3], B[i].x, B[i].y);
        if ((lane & 3) == 0) {
            sts1(wmbuf + 29696 + (wp * 32 + pn * 16 + (lane >> 2)) * 4, __float_as_uint(d[0]));
            sts1(wmbuf + 29696 + (wp * 32 + pn * 16 + 8 + (lane >> 2)) * 4, __float_as_uint(d[2]));
        }
    }
}
__device__ __forceinline__ const uint4* mod_src(int i, int r, int j, bool p2) {
    i = min(i, p2 ? 251 : 223);
    return (const uint4*)g_mod + (r & 7) * (6 * DM / 4) + (i < 224 ? (p2 ? 336 : 0) + i : (i < 238 ? 14 * j + i : 14 * j + i + 322));
}
__device__ __forceinline__ void mod_store(uint32_t sb, uint4 v, const uint4* src, int i, uint32_t sc) {
    const uint32_t tag = lds1(sb + M_EPOCH) + 1;
    while (__any_sync(~0u, (((v.x ^ tag) | (v.y ^ tag) | (v.z ^ tag) | (v.w ^ tag)) & 0xFFFFu) != 0u) && !sc) v = ld_relaxed4(src);
    if (i < 224) {
        const int isc = i >= 112, c4 = i - 112 * isc;
        const uint32_t a = sb + M_ST + (c4 >> 2) * 64 + (c4 & 1) * 32 + (c4 & 2) * 4 + (isc ? 0 : 4);
        sts1(a, __byte_perm(v.x, v.y, 0x7632));
        sts1(a + 16, __byte_perm(v.z, v.w, 0x7632));
    } else if (i < 252) {
        sts4(sb + M_G + (i - 224) * 16, make_uint4(v.x & 0xFFFF0000u, v.y & 0xFFFF0000u, v.z & 0xFFFF0000u, v.w & 0xFFFF0000u));
    }
}
__device__ __forceinline__ int pass_f(int fs, int ps) { return 224 * fs + ((fs & 1) ? (ps == 0 ? 96 : ps == 1 ? 32 : 0) : (ps == 0 ? 0 : ps == 1 ? 128 : 192)); }
__device__ __forceinline__ constexpr uint32_t slot_off(int l) { return l * 16384; }
__device__ __forceinline__ constexpr int g1_slot(int s) { return s < 3 ? s : s < 6 ? s + 1 : s == 6 ? 3 : s % 7; }
__device__ __noinline__ void x1_fix(const uint32_t* g, uint32_t sa, int s) {
#pragma unroll 1
    for (int k = 4 * s; k < 4 * s + 4;) {
        const uint4 v = ld_relaxed4((const uint4*)(g + k * 256));
        sts4(sa + k * 1024, v);
        k += 2 * __all_sync(~0u, min(min(v.x, v.y), min(v.z, v.w)) != 0u);
    }
    __syncwarp();
}
__device__ __forceinline__ void ln_coeffs(float mean, float msq, uint32_t& r2, uint32_t& n2) {
    const float rs = bf_round(rsqrtf(fmaxf(msq - mean * mean, 0.f) + 1e-5f));
    r2 = pack2(rs, rs);
    n2 = pack2(-mean * rs, -mean * rs);
}

#define LOADW bulk_e(dst, g_wd + (size_t)((f >> 5) * 4 + nq) * 1792, 7168, bar);
template <int sec> __device__ __forceinline__ void ring_loader(const Params& p, uint32_t sb_, int r_, int j_, int lane) {
    const uint32_t sb = opaque(sb_);
    const int r = opaque(r_), j = opaque(j_), nq = j >> 1, fs = 4 * (j & 1) + nq;
    const int fa = pass_f(fs, 0), fb = pass_f(fs, 1), fc = pass_f(fs, 2);
#define BAR(i) (sb + M_BAR + 8 * (i))
#define kh (j & 1)
            int sl = 0;
            mbar_wait(BAR(B_PUB + 2), 0);
            wait_flags(g_flag + (8 * r + j) * 128 + 96 + lane, lds1(sb + M_EPOCH) + 1, 0xFFFFu);
            fence_async_global();
#pragma unroll 1
            for (int s = 0; s < 28; s++) {
                const int ps = s < 14 ? 0 : s < 21 ? 1 : 2;
                const uint32_t half = ps < 2 ? 8192 : 4096;
                const int sp = s >= 3 && s < 7 ? (s == 6 ? 3 : s + 1) : sl;
                mbar_wait(BAR(B_EMPTY + sp), (s >= 7 && s < 14) || s >= 21);
                expect_e(BAR(B_FULL + sp), half);
                tma3_e(sb + slot_off(sp) + sec * half, &p.ga + 2 * ps + sec, 0, ps ? 64 * sl : 32 * s, ps == 0 ? fa >> 6 : ps == 1 ? fb >> 6 : fc >> 5, BAR(B_FULL + sp));
                sl = sl == 6 ? 0 : sl + 1;
            }
            if (!sec) PROFH(3);
#pragma unroll 1
            for (int e = 0; e < 4; e++) {
                const uint32_t dst = sb + slot_off(e) + sec * 8192, bar = BAR(B_FULL + e);
                const int f = (e < 2 ? fa + 64 * e : e == 2 ? fb : fc) + 32 * sec;
                mbar_wait(BAR(B_EMPTY + e), 0);
                expect_e(bar, e == 3 && sec ? 0 : 7168);
                if (!(e == 3 && sec)) { LOADW }
            }
            sl = 4;
            int e = 4;
#pragma unroll 1
            for (int grp = 0; grp < 9; grp++) {
                const int ps = grp >= 6 ? 2 : grp >= 3 ? 1 : 0;
                int sidx = grp - 3 * ps;
                if (sec && sidx == 0) { mbar_wait(BAR(B_HRDY + ps), 0); fence_async_global(); }
                sidx += sidx >= nq;
                int f = pass_f(4 * kh + sidx, ps);
#pragma unroll 1
                for (int k = 4 >> ps; k > 0; k--, e++, f += 32) {
                    const uint32_t dst = sb + slot_off(sl), bar = BAR(B_FULL + sl);
                    mbar_wait(BAR(B_EMPTY + sl), e >= 12 && e < 24);
                    if (e < WIN_END && e >= WIN) mbar_wait(BAR(B_FULL + (sl >= WIN ? sl - WIN : sl + 12 - WIN)), e - WIN >= 12);
                    expect_e(bar, sec ? 8192 : 7168);
                    if (!sec) { LOADW }
                    else bulk_e(dst + 8192, p.actb + (size_t)r * RB_WORDS + RB_H2 + f * 64, 8192, bar);
                    sl = sl == 11 ? 0 : sl + 1;
                }
            }
            if (!sec) PROFH(4);
}

__global__ void __cluster_dims__(2, 1, 1) __launch_bounds__(384, 1) fused_block_kernel(const __grid_constant__ Params p) {
    extern __shared__ __align__(1024) unsigned char smem[];
    const uint32_t sb = (uint32_t)__cvta_generic_to_shared(smem);
    const int tid = threadIdx.x, lane = tid & 31, warp = __shfl_sync(~0u, tid >> 5, 0);
    const int m = blockIdx.x >> 1;
    int r, nq;
    {
        int g, i;
        if (m < MAP_S) { g = m < 4 ? 15 : 16; i = m & 3; }
        else if (m < MAP_S + 32) { g = (m - MAP_S) & 7; i = (m - MAP_S) >> 3; }
        else if (m < MAP_S + 60) { i = (m - MAP_S - 32) / 7; g = 8 + (m - MAP_S - 32) - 7 * i; }
        else { g = 16; i = m & 3; }
        r = g; nq = i;
    }
    const int j = opaque(2 * nq + (blockIdx.x & 1)), b = 8 * r + j, fs = 4 * kh + nq;
#define act (p.actb + (size_t)r * RB_WORDS)
    const uint32_t sc = r == 16;
    if (lane == 0 && warp < 9 && warp != 6 && warp != 7) {
        const int i0 = warp == 8 ? 0 : 8 + 8 * warp, cnt = warp == 0 || warp == 8 ? 1 : warp < 3 ? 2 : 8;
#pragma unroll
        for (int k = 0; k < 8; k++) if (i0 + k != B_WMFULL) mbar_init(BAR(i0 + k), cnt);
        asm volatile("fence.mbarrier_init.release.cluster;" ::: "memory");
        fence_async_smem();
    }

    if (warp < 8) {
        const int w = warp >> 2, wi = warp & 3;
#define COORDS const int t = fresh_tid() & 127, lane = t & 31, q = lane & 3, lr = lane >> 2, ra = 64 * w + 16 * wi + lr; \
        const uint32_t lx = (lane >> 4) ^ (lane & 7), mrow = (64 * w + 16 * wi + ((lane >> 3) & 1) * 8 + (lane & 7)) * 128; \
        (void)q; (void)lr; (void)ra; (void)lx; (void)mrow;
        const int sid = 2 * (j & 3) + w;
#define RUN(k) (!sc || sid == (k))
#define WAIT(i, par) mbar_wait_c(BAR(i), (par) | sc)
        constexpr uint64_t DB128 = dconst(4096, 1024, 1);
        {
            const int wd = fresh_tid();
            const uint32_t cb = wd < 224 ? __ldg((const uint32_t*)p.c + wd) : 0u;
            if (wd == 255 && !sc) sts1(sb + M_EPOCH, atomicAdd(&g_ticket, 1u) / NCTA);
            sts1(sb + OFF_Y + HALF + 28672 + (wd >> 3) * 32 + (wd & 3) * 8 + (wd & 4), pack2(silu_bf(cb & 0xFFFFu), silu_bf(cb >> 16)));
        }
        bar_arrive(9, 384);
        bar_sync(0, 384);
        asm volatile("barrier.cluster.arrive.relaxed.aligned;" ::: "memory");
        asm volatile("setmaxnreg.inc.sync.aligned.u32 224;");
        PROFC(0);
        uint32_t xr[16];
        {
            COORDS
            uint32_t h[112];
            if (RUN(0)) {
                float ds[4] = {}, da[2][4] = {}, db[2][4] = {};
                const uint32_t ONE2 = 0x3F803F80u;
                if (kh == 0) { WAIT(B_WMFULL, 0); gemv_part(sb + OFF_Y + HALF, 1, warp, lane); warp_arrive(BAR(B_GEMV)); }
#pragma unroll
                for (int kb = 0; kb < 7; kb++) {
                    WAIT(B_XFULL + kb, 0);
#pragma unroll
                    for (int k4 = 0; k4 < 4; k4++) ldsm4(sb + OFF_X + mrow + kb * 16384 + (((2 * k4) ^ lx) << 4), h + 16 * kb + 4 * k4);
#pragma unroll
                    for (int k4 = 0; k4 < 4; k4++) {
                        const uint32_t* f = h + 16 * kb + 4 * k4;
                        mma16816(ds, f[0], f[1], f[2], f[3], ONE2, ONE2);
                        mma1688(da[0], f[0], f[1], f[0]); mma1688(db[0], f[0], f[1], f[1]);
                        mma1688(da[1], f[2], f[3], f[2]); mma1688(db[1], f[2], f[3], f[3]);
                    }
                }
#pragma unroll
                for (int i = 0; i < 4; i++) {
                    const int ch = 7 * j + 2 * i + (lane >> 4);
                    ldsm4(sb + OFF_X + mrow + (ch >> 3) * 16384 + (((ch ^ lane) & 7) << 4), xr + 4 * i);
                }
                warp_arrive(BAR(B_XFREE));
                float qa = (lr & 1) ? da[0][1] + da[1][1] : da[0][0] + da[1][0];
                float qb = (lr & 1) ? db[0][3] + db[1][3] : db[0][2] + db[1][2];
                const int src = (lane & ~3) | (lr >> 1);
                qa = __shfl_sync(~0u, qa, src);
                qb = __shfl_sync(~0u, qb, src);
                uint32_t ra2, na2, rb2, nb2;
                ln_coeffs(ds[0] * (1.f / DM), qa * (1.f / DM), ra2, na2);
                ln_coeffs(ds[2] * (1.f / DM), qb * (1.f / DM), rb2, nb2);
#pragma unroll
                for (int i = 0; i < 112; i += 2) { h[i] = hfma2(h[i], ra2, na2); h[i + 1] = hfma2(h[i + 1], rb2, nb2); }
                if (kh == 1) { WAIT(B_WMFULL, 0); gemv_part(sb + OFF_Y + HALF, 2, warp, lane); warp_arrive(BAR(B_GEMV)); }
            } else { reg_def<112>(h); reg_def<16>(xr); }
            PROFC(1);
            if (RUN(1)) {
                float ak[28], av[28], aq[28];
                uint32_t kp[14], vp[14];
                const uint32_t bk0 = mkdesc(sb + OFF_Y, DB128) + kh, bv0 = mkdesc(sb + OFF_Y + HALF, DB128) + kh, bq0 = mkdesc(sb + OFF_X, DB128) + kh;
                uint32_t* kvg = act + RB_KV + j * 7168 + (8 * w + 2 * wi) * 224 + lane;
                {
                    const int i = min(fresh_tid(), 223);
                    const uint4* src = mod_src(i, r, j, false);
                    mod_store(sb, ld_relaxed4(src), src, i, sc);
                    if (!sc) bar_sync(3, 256);
                    if (warp == 0) warp_arrive(BAR(B_MOD1));
                }
                WAIT(B_FULLK, 0);
                PROFC(2);
                reg_def<28>(ak);
#pragma unroll
                for (int g4 = 0; g4 < 4; g4++) {
#pragma unroll
                    for (int ks = 7 * g4; ks < 7 * g4 + 7; ks++) {
                        const uint4 st = *(const uint4*)(smem + M_ST + ks * 64 + q * 16);
                        h[4 * ks] = hfma2(h[4 * ks], st.x, st.y); h[4 * ks + 1] = hfma2(h[4 * ks + 1], st.x, st.y);
                        h[4 * ks + 2] = hfma2(h[4 * ks + 2], st.z, st.w); h[4 * ks + 3] = hfma2(h[4 * ks + 3], st.z, st.w);
                    }
                    WG_FENCE();
#pragma unroll
                    for (int ks = 7 * g4; ks < 7 * g4 + 7; ks++) wgmma_rs_56<DB128>(ak, h[4 * ks], h[4 * ks + 1], h[4 * ks + 2], h[4 * ks + 3], bk0 + ks * 128, ks != 0);
                }
                WG_COMMIT();
                PROFC(3);
                WAIT(B_FULLV, 0);
                reg_def<28>(av);
                WG_FENCE();
#pragma unroll
                for (int ks = 0; ks < 8; ks++) wgmma_rs_56<DB128>(av, h[4 * ks], h[4 * ks + 1], h[4 * ks + 2], h[4 * ks + 3], bv0 + ks * 128, ks != 0);
                WG_COMMIT();
                WG_WAIT(1);
                reg_fence<28>(ak);
#pragma unroll
                for (int g = 0; g < 7; g++) {
                    kp[2 * g] = pack2(ak[4 * g], ak[4 * g + 1]); kp[2 * g + 1] = pack2(ak[4 * g + 2], ak[4 * g + 3]);
                    kvg[g * 32] = kp[2 * g]; kvg[224 + g * 32] = kp[2 * g + 1];
                }
                warp_arrive(BAR(B_PUB));
                PROFC(4);
                WG_FENCE();
#pragma unroll
                for (int ks = 8; ks < 28; ks++) wgmma_rs_56<DB128>(av, h[4 * ks], h[4 * ks + 1], h[4 * ks + 2], h[4 * ks + 3], bv0 + ks * 128, 1);
                WG_COMMIT();
                WAIT(B_FULLQ, 0);
                reg_def<28>(aq);
                WG_FENCE();
#pragma unroll
                for (int ks = 0; ks < 8; ks++) wgmma_rs_56<DB128>(aq, h[4 * ks], h[4 * ks + 1], h[4 * ks + 2], h[4 * ks + 3], bq0 + ks * 128, ks != 0);
                WG_COMMIT();
                WG_WAIT(1);
                reg_fence<28>(av);
#pragma unroll
                for (int g = 0; g < 7; g++) {
                    vp[2 * g] = pack2(av[4 * g], av[4 * g + 1]); vp[2 * g + 1] = pack2(av[4 * g + 2], av[4 * g + 3]);
                    kvg[3584 + g * 32] = vp[2 * g]; kvg[3584 + 224 + g * 32] = vp[2 * g + 1];
                }
                warp_arrive(BAR(B_PUB + 1));
                const uint4* msrc = mod_src(128 * w + t, r, j, true);
                const uint4 mv = ld_relaxed4(msrc);
                PROFC(5);
                WG_FENCE();
#pragma unroll
                for (int ks = 8; ks < 28; ks++) wgmma_rs_56<DB128>(aq, h[4 * ks], h[4 * ks + 1], h[4 * ks + 2], h[4 * ks + 3], bq0 + ks * 128, 1);
                WG_COMMIT();
                WAIT(B_PUB + 1, 0);
                mod_store(sb, mv, msrc, 128 * w + t, sc);
                const uint32_t ko = sb + OFF_Y + Y_KOWN + (8 * w + 2 * wi) * 896 + lane * 4;
                const uint32_t qo = sb + OFF_Y + Y_Q + (8 * w + 2 * wi) * 1024 + lane * 4;
#pragma unroll
                for (int g = 0; g < 7; g++) {
                    sts1(ko + g * 128, kp[2 * g]); sts1(ko + 896 + g * 128, kp[2 * g + 1]);
                    sts1(ko + (Y_VOWN - Y_KOWN) + g * 128, vp[2 * g]); sts1(ko + (Y_VOWN - Y_KOWN) + 896 + g * 128, vp[2 * g + 1]);
                }
                WG_WAIT(0);
                reg_fence<28>(aq);
                __syncwarp();
                if (lane < 3 && w == 1) mbar_arrive(BAR(B_EMPTY + lane));
#pragma unroll
                for (int g = 0; g < 7; g++) {
                    const uint32_t q0 = pack2(aq[4 * g], aq[4 * g + 1]), q1 = pack2(aq[4 * g + 2], aq[4 * g + 3]);
                    if (g == 3) {
                        sts1(qo + 3 * 128, q < 2 ? q0 : 0u); sts1(qo + 1024 + 3 * 128, q < 2 ? q1 : 0u);
                        sts1(qo + 4 * 128, q < 2 ? 0u : q0); sts1(qo + 1024 + 4 * 128, q < 2 ? 0u : q1);
                    } else {
                        const int ch = g < 3 ? g : g + 1;
                        sts1(qo + ch * 128, q0); sts1(qo + 1024 + ch * 128, q1);
                    }
                }
                if (!sc) bar_sync(3, 256);
            }
        }
        PROFC(6);
        WAIT(B_KRFULL, 0);
        PROFC(7);
        if (RUN(2)) {
#pragma unroll 1
            for (int hf = sc; hf < 2; hf++) {
                COORDS
                float s[136];
                float na = 0.f, nb = 0.f;
                const float CS = 0.18898223650461361f * 1.4426950408889634f;
                const int kg0 = 8 * hf + 2 * wi;
                const int pmin = 16 - 8 * r - 4 * hf - wi;
                const float NEG = __int_as_float(0xFF800000);
                {
                    uint32_t F[8];
                    const uint32_t qa = sb + OFF_Y + Y_Q + (kg0 + ((lane >> 3) & 1)) * 1024 + (4 * w + (lane >> 4)) * 128 + (lane & 7) * 16;
                    ldsm4(qa, F); ldsm4(qa + 256, F + 4);
                    uint32_t ka = sb + OFF_Y + Y_K + kg0 * 896 + (3 * w + (lane >> 3)) * 128 + (lane & 7) * 16;
#pragma unroll
                    for (int g = 0; g < 34; g++) {
                        uint32_t B[4];
                        if (g >= 12 && g % 4 == 0) ka += __float_as_uint(s[4 * (g - 12)]) & p.zero;
                        ldsm4(ka + g * 896, B);
                        mma16816_first(s + 4 * g, F[0], F[1], F[2], F[3], B[0], B[1]);
                        mma16816_v(s + 4 * g, F[4], F[5], F[6], F[7], B[2], B[3]);
                    }
                    const bool c0 = 2 * q > lr, c1 = 2 * q + 1 > lr;
                    if (!c0) { s[0] = NEG; s[6] = NEG; }
                    if (!c1) { s[1] = NEG; s[7] = NEG; }
                    s[2] = NEG; s[3] = NEG;
                    if (c0) { s[128] = NEG; s[134] = NEG; }
                    if (c1) { s[129] = NEG; s[135] = NEG; }
                    s[132] = NEG; s[133] = NEG;
                    float ma = NEG, mb = NEG;
#pragma unroll
                    for (int pp = 0; pp < 17; pp++) {
                        const float* e = s + 8 * pp;
                        const float bias = pp < pmin ? NEG : 0.f;
                        ma = fmaxf(ma, fmaxf(fmaxf(e[0], e[1]), fmaxf(e[4], e[5])) + bias);
                        mb = fmaxf(mb, fmaxf(fmaxf(e[2], e[3]), fmaxf(e[6], e[7])) + bias);
                    }
                    ma = fmaxf(ma, __shfl_xor_sync(~0u, ma, 1)); mb = fmaxf(mb, __shfl_xor_sync(~0u, mb, 1));
                    ma = fmaxf(ma, __shfl_xor_sync(~0u, ma, 2)); mb = fmaxf(mb, __shfl_xor_sync(~0u, mb, 2));
                    na = -ma * CS; nb = -mb * CS;
                }
                PROFC(8 + 3 * hf);
                {
                    WAIT(B_VRFULL, 0);
                    float o[16] = {}, rs[4] = {};
                    uint32_t pk[2];
                    const uint32_t va = sb + OFF_Y + Y_VR + (kg0 + ((lane >> 3) & 1)) * 896 + (3 * w + (lane >> 4)) * 128 + (lane & 7) * 16;
#pragma unroll
                    for (int pp = 0; pp < 17; pp++) {
                        uint32_t B[8];
                        const uint32_t v = va + pp * 1792 + (pp == 16 || (pp >= 9 && kg0 + 2 * pp >= 32) ? Y_VOWN - 32 * 896 : 0);
                        ldsm4t(v, B); ldsm4t(v + 256, B + 4);
                        float e[8];
                        const float bias = __uint_as_float((pp < pmin ? 0xFF800000u : 0u) | ((pp < 2 ? B[0] : pk[pp & 1]) & p.zero));
#pragma unroll
                        for (int i = 0; i < 8; i++) e[i] = ex2(fmaf(s[8 * pp + i], CS, ((i & 2) ? nb : na) + bias));
                        const uint32_t p0 = pack2(e[0], e[1]), p1 = pack2(e[2], e[3]), p2 = pack2(e[4], e[5]), p3 = pack2(e[6], e[7]);
                        pk[pp & 1] = p3;
                        mma16816(rs, p0, p1, p2, p3, 0x3F803F80u, 0x3F803F80u);
#pragma unroll
                        for (int g = 0; g < 4; g++) mma16816(o + 4 * g, p0, p1, p2, p3, B[2 * g], B[2 * g + 1]);
                    }
                    PROFC(9 + 3 * hf);
                    const float ia = rcp(rs[0]), ib = rcp(rs[2]);
                    uint32_t* og = act + RB_O + hf * 14336 + (7 * j + 3 * w) * 256 + wi * 64 + lane;
#pragma unroll
                    for (int g = 0; g < 4; g++) {
                        if ((g == 3 - 3 * w) ? ((q >> 1) == w) : true) {
                            og[g * 256] = pack2(o[4 * g] * ia, o[4 * g + 1] * ia);
                            og[g * 256 + 32] = pack2(o[4 * g + 2] * ib, o[4 * g + 3] * ib);
                        }
                    }
                    warp_arrive(BAR(B_PUB + 2 + hf));
                    PROFC(10 + 3 * hf);
                }
            }
        }
        uint32_t x1p[14];
        COORDS
        constexpr uint64_t DT = dconst(1024, 128, 0);
        const int tile = opaque((lds1(sb + M_EPOCH) & 1) * 2 + w);
        if (RUN(4)) {
            float ac[28];
            const uint32_t ad = mkdesc(sb + (w ? OFF_Y + HALF : OFF_X), DT), bd = mkdesc(sb + OFF_X + HALF, DB128) + kh;
            WAIT(B_WOFULL, 0);
            WAIT(B_GFULL + w, 0);
            PROFC(28);
            reg_def<28>(ac);
#pragma unroll 1
            for (int u = 0; u < 4; u++) {
                if (u == 2) WAIT(B_XFULL + 2 + w, 1);
                WG_FENCE();
#pragma unroll
                for (int i = 0; i < 7; i++) wgmma_ss_56<DT, DB128>(ac, ad + (7 * u + i) * 128, bd + (7 * u + i) * 128, (u | i) != 0);
            }
            WG_COMMIT();
            WG_WAIT(0);
            reg_fence<28>(ac);
            PROFC(14);
            __syncwarp();
            if (lane < 3) mbar_arrive(BAR(B_EMPTY + 4 + lane));
            if (lane < 3 && w == 0) mbar_arrive(BAR(B_EMPTY + lane));
            float s1a = 0.f, s2a = 0.f, s1b = 0.f, s2b = 0.f;
            uint32_t* xo = act + RB_X1 + tile * 14336 + 7 * j * 256 + wi * 64 + lane;
#pragma unroll
            for (int g = 0; g < 7; g++) {
                const float2 ga = *(const float2*)(smem + M_G + (8 * g + 2 * q) * 4);
                x1p[2 * g] = pack2(fmaf(ga.x, ac[4 * g], bf_lo(xr[2 * g])), fmaf(ga.y, ac[4 * g + 1], bf_hi(xr[2 * g])));
                x1p[2 * g + 1] = pack2(fmaf(ga.x, ac[4 * g + 2], bf_lo(xr[2 * g + 1])), fmaf(ga.y, ac[4 * g + 3], bf_hi(xr[2 * g + 1])));
                st_relaxed(xo + g * 256, max(x1p[2 * g], 1u)); st_relaxed(xo + g * 256 + 32, max(x1p[2 * g + 1], 1u));
                const float u0 = bf_lo(x1p[2 * g]), u1 = bf_hi(x1p[2 * g]), u2 = bf_lo(x1p[2 * g + 1]), u3 = bf_hi(x1p[2 * g + 1]);
                s1a += u0 + u1; s2a += u0 * u0 + u1 * u1; s1b += u2 + u3; s2b += u2 * u2 + u3 * u3;
            }
            float ka = (q & 1) ? s2a : s1a, kb2 = (q & 1) ? s2b : s1b;
            ka += __shfl_xor_sync(~0u, (q & 1) ? s1a : s2a, 1); kb2 += __shfl_xor_sync(~0u, (q & 1) ? s1b : s2b, 1);
            const float kk = ((q & 2) ? kb2 : ka) + __shfl_xor_sync(~0u, (q & 2) ? ka : kb2, 2);
            st_relaxed(act + RB_ST + ((tile * 8 + j) * 64 + 16 * wi + lr + 4 * (q & 2)) * 2 + (q & 1), max(__float_as_uint(kk), 1u));
            __syncwarp();
            if (lane < 2) mbar_arrive(BAR(B_PUB + 4 + w));
        } else reg_def<14>(x1p);
        PROFC(15);
        uint32_t h2a[32], h2b[24];
        {
            const int fa = pass_f(fs, 0), fb = pass_f(fs, 1), fc = pass_f(fs, 2);
            uint32_t* h2g = act + RB_H2 + (8 * w + 2 * wi) * 32 + lane;
            const uint32_t a0 = mkdesc(sb + OFF_Y + w * HALF, DT);
            if (RUN(3)) {
                uint32_t ra2, na2, rb2, nb2;
                {
                    const uint32_t* sg = act + RB_ST + ((tile * 8 + 2 * q) * 64 + 16 * wi + lr) * 2;
                    uint2 u[4];
                    WAIT(B_GFULL + 2 + w, 0);
                    PROFC(16);
#pragma unroll
                    for (int i = 0; i < 4; i++) { const float2 v = lds2f(sb + OFF_X + X_STAT + w * 4096 + ((2 * q + (i >> 1)) * 64 + 16 * wi + lr + 8 * (i & 1)) * 8); u[i] = make_uint2(__float_as_uint(v.x), __float_as_uint(v.y)); }
                    while (__any_sync(~0u, min(min(min(u[0].x, u[0].y), min(u[1].x, u[1].y)), min(min(u[2].x, u[2].y), min(u[3].x, u[3].y))) < 1u - sc)) {
#pragma unroll
                        for (int i = 0; i < 4; i++) u[i] = ld_relaxed2(sg + (i >> 1) * 128 + (i & 1) * 16);
                    }
                    warp_arrive(BAR(B_EMPTY + 3));
                    float v[4] = {__uint_as_float(u[0].x) + __uint_as_float(u[2].x), __uint_as_float(u[0].y) + __uint_as_float(u[2].y),
                                  __uint_as_float(u[1].x) + __uint_as_float(u[3].x), __uint_as_float(u[1].y) + __uint_as_float(u[3].y)};
#pragma unroll
                    for (int i = 0; i < 4; i++) { v[i] += __shfl_xor_sync(~0u, v[i], 1); v[i] += __shfl_xor_sync(~0u, v[i], 2); }
                    ln_coeffs(v[0] * (1.f / DM), v[1] * (1.f / DM), ra2, na2);
                    ln_coeffs(v[2] * (1.f / DM), v[3] * (1.f / DM), rb2, nb2);
                }
                const uint32_t ha = sb + OFF_Y + w * HALF + (lane >> 4) * 1024 + (2 * wi + ((lane >> 3) & 1)) * 128 + (lane & 7) * 16;
                const uint32_t sta = sb + M_ST + q * 16;
                const uint32_t* xg = act + RB_X1 + tile * 14336 + (lane >> 4) * 256 + wi * 64 + (lane & 15) * 4;
                uint32_t x[8];
                const uint32_t xs = sb + OFF_Y + w * HALF + (lane >> 4) * 1024 + wi * 256 + (lane & 15) * 16;
                uint4 st[2];
                auto load = [&](int s) {
                    if (s == 4) mbar_wait_c(BAR(B_XFULL + 4 + w), 1);
                    ldsm4(ha + s * 4096, x); ldsm4(ha + s * 4096 + 2048, x + 4);
                    st[0] = lds4(sta + s * 128); st[1] = lds4(sta + s * 128 + 64);
                };
                auto prep = [&](int s, uint32_t* f) {
                    if (__any_sync(~0u, min(min(min(x[0], x[1]), min(x[2], x[3])), min(min(x[4], x[5]), min(x[6], x[7]))) < 1u - sc)) {
                        WG_WAIT(0);
                        x1_fix(xg, xs, s);
                        ldsm4(ha + s * 4096, x); ldsm4(ha + s * 4096 + 2048, x + 4);
                    }
#pragma unroll
                    for (int i = 0; i < 2; i++) {
                        f[4 * i] = hfma2(hfma2(x[4 * i], ra2, na2), st[i].x, st[i].y); f[4 * i + 1] = hfma2(hfma2(x[4 * i + 1], rb2, nb2), st[i].x, st[i].y);
                        f[4 * i + 2] = hfma2(hfma2(x[4 * i + 2], ra2, na2), st[i].z, st[i].w); f[4 * i + 3] = hfma2(hfma2(x[4 * i + 3], rb2, nb2), st[i].z, st[i].w);
                    }
                    if (s < 13) load(s + 1);
                    stsm4(ha + s * 4096, f[0], f[1], f[2], f[3]); stsm4(ha + s * 4096 + 2048, f[4], f[5], f[6], f[7]);
                };
                float ac[128];
                uint32_t fr[3][8];
                const uint32_t bx = mkdesc(sb, DB128);
                reg_def<128>(ac);
                load(0);
                prep(0, fr[0]);
                PROFC(17);
#pragma unroll
                for (int s = 0; s < 14; s++) {
                    const uint32_t* f = fr[s % 3];
                    const uint32_t bd = bx + g1_slot(s) * 1024;
                    WAIT(B_FULL + g1_slot(s), s >= 7);
                    WG_FENCE();
                    wgmma_rs_256<DB128>(ac, f[0], f[1], f[2], f[3], bd, s != 0);
                    wgmma_rs_256<DB128>(ac, f[4], f[5], f[6], f[7], bd + 128, 1);
                    WG_COMMIT();
                    if (s < 13) prep(s + 1, fr[(s + 1) % 3]);
                    if (s > 0) { WG_WAIT(1); warp_arrive(BAR(B_EMPTY + g1_slot(s - 1))); }
                }
                fence_async_smem();
                PROFC(18);
                WG_WAIT(0);
                reg_fence<128>(ac);
                warp_arrive(BAR(B_EMPTY + 6));
#pragma unroll
                for (int g = 0; g < 16; g++) {
                    h2a[2 * g] = hmul2(pack2_relu(ac[4 * g], ac[4 * g + 1]), pack2(ac[64 + 4 * g], ac[64 + 4 * g + 1]));
                    h2a[2 * g + 1] = hmul2(pack2_relu(ac[4 * g + 2], ac[4 * g + 3]), pack2(ac[64 + 4 * g + 2], ac[64 + 4 * g + 3]));
                    h2g[(fa / 8 + g) * 512] = h2a[2 * g]; h2g[(fa / 8 + g) * 512 + 32] = h2a[2 * g + 1];
                }
                warp_arrive(BAR(B_PUB + 6));
                bar_sync(1 + w, 128);
            } else reg_def<32>(h2a);
            PROFC(19);
            if (RUN(5)) {
                float ac[64];
                reg_def<64>(ac);
                const uint32_t bx = mkdesc(sb, dconst(8192, 1024, 1));
#pragma unroll kB
                for (int s = 0; s < 7; s++) {
                    WAIT(B_FULL + s, 0);
                    const uint32_t ad = a0 + s * 512, bd = bx + (slot_off(s) >> 4);
                    WG_FENCE();
#pragma unroll
                    for (int k = 0; k < 4; k++) wgmma_ss_128<DT, DB128>(ac, ad + k * 128, bd + k * 128, (s | k) != 0);
                    WG_COMMIT();
                    if (s > 0) { WG_WAIT(1); warp_arrive(BAR(B_EMPTY + s - 1)); }
                }
                WG_WAIT(0);
                reg_fence<64>(ac);
                warp_arrive(BAR(B_EMPTY + 6));
#pragma unroll
                for (int g = 0; g < 8; g++) {
                    h2b[2 * g] = hmul2(pack2_relu(ac[4 * g], ac[4 * g + 1]), pack2(ac[32 + 4 * g], ac[32 + 4 * g + 1]));
                    h2b[2 * g + 1] = hmul2(pack2_relu(ac[4 * g + 2], ac[4 * g + 3]), pack2(ac[32 + 4 * g + 2], ac[32 + 4 * g + 3]));
                    h2g[(fb / 8 + g) * 512] = h2b[2 * g]; h2g[(fb / 8 + g) * 512 + 32] = h2b[2 * g + 1];
                }
                warp_arrive(BAR(B_PUB + 7));
            } else reg_def<16>(h2b);
            PROFC(27);
            if (RUN(6)) {
                float ac[32];
                reg_def<32>(ac);
                const uint32_t bx = mkdesc(sb, dconst(4096, 512, 2));
#pragma unroll kC
                for (int s = 0; s < 7; s++) {
                    WAIT(B_FULL + s, 1);
                    const uint32_t ad = a0 + s * 512, bd = bx + (slot_off(s) >> 4);
                    WG_FENCE();
#pragma unroll
                    for (int k = 0; k < 4; k++) wgmma_ss_64<DT, dconst(4096, 512, 2)>(ac, ad + k * 128, bd + k * 64, (s | k) != 0);
                    WG_COMMIT();
                    if (s > 0) { WG_WAIT(1); warp_arrive(BAR(B_EMPTY + s - 1)); }
                }
                WG_WAIT(0);
                reg_fence<32>(ac);
                __syncwarp();
                if (lane < 6) mbar_arrive(BAR(B_EMPTY + 6 + lane));
                PROFC(20);
#pragma unroll
                for (int g = 0; g < 4; g++) {
                    h2b[16 + 2 * g] = hmul2(pack2_relu(ac[4 * g], ac[4 * g + 1]), pack2(ac[16 + 4 * g], ac[16 + 4 * g + 1]));
                    h2b[16 + 2 * g + 1] = hmul2(pack2_relu(ac[4 * g + 2], ac[4 * g + 3]), pack2(ac[16 + 4 * g + 2], ac[16 + 4 * g + 3]));
                    h2g[(fc / 8 + g) * 512] = h2b[16 + 2 * g]; h2g[(fc / 8 + g) * 512 + 32] = h2b[16 + 2 * g + 1];
                }
                warp_arrive(BAR(B_PUB + 8));
                asm volatile("barrier.cluster.wait.aligned;" ::: "memory");
                if (lane == 0 && !sc) {
                    uint32_t rb;
                    asm volatile("mapa.shared::cluster.u32 %0, %1, %2;" : "=r"(rb) : "r"(BAR(B_PEER)), "r"(kh ^ 1));
                    asm volatile("mbarrier.arrive.relaxed.cluster.shared::cluster.b64 _, [%0];" ::"r"(rb) : "memory");
                }
            } else reg_def<8>(h2b + 16);
        }
        PROFC(21);
        if (RUN(7)) {
            float ac[56];
            reg_def<56>(ac);
            constexpr uint64_t DAN = dconst(2048, 128, 0);
            constexpr uint64_t DW = dconst(128, 512, 0);
            const uint32_t bx = mkdesc(sb, DW);
#pragma unroll
            for (int e = 0; e < 4; e++) {
                WAIT(B_FULL + e, 0);
                const uint32_t bd = bx + (slot_off(e) >> 4);
                const uint32_t* hh = e < 2 ? h2a + 16 * e : h2b + 16 * (e - 2);
                WG_FENCE();
#pragma unroll
                for (int k = 0; k < (e < 3 ? 4 : 2); k++) wgmma_rs_112<DW>(ac, hh[4 * k], hh[4 * k + 1], hh[4 * k + 2], hh[4 * k + 3], bd + (k >> 1) * 512 + (k & 1) * 16, (e | k) != 0);
                WG_COMMIT();
                if (e > 0) { WG_WAIT(1); warp_arrive(BAR(B_EMPTY + e - 1)); }
            }
            PROFC(22);
            uint32_t ad = mkdesc(sb + 4 * 16384 + 8192 + w * 1024, DAN), bd = bx + 4 * 1024, fb_ = BAR(B_FULL + 4), eb_ = BAR(B_EMPTY + 3), par = sc;
#pragma unroll 1
            for (int e = 4; e < 25; e++) {
                mbar_wait_c(fb_, par);
                WG_FENCE();
                wgmma_ss_112<DAN, DW>(ac, ad, bd, 1);
                wgmma_ss_112<DAN, DW>(ac, ad + 256, bd + 16, 1);
                WG_COMMIT();
                WG_WAIT(1);
                warp_arrive(eb_);
                eb_ = fb_ + 8 * (B_EMPTY - B_FULL);
                ad += 1024; bd += 1024; fb_ += 8;
                if (e == 11 || e == 23) { ad -= 12 * 1024; bd -= 12 * 1024; fb_ -= 96; par = (par ^ 1) | sc; }
            }
            mbar_wait_cluster(BAR(B_PEER), sc);
            WG_WAIT(0);
            reg_fence<56>(ac);
            PROFC(24);
            uint32_t rdst, rbar;
            asm volatile("mapa.shared::cluster.u32 %0, %1, %2;" : "=r"(rdst) : "r"(sb + OFF_Y + (5 + w) * 16384 + t * 16), "r"(kh ^ 1 ^ sc));
            asm volatile("mapa.shared::cluster.u32 %0, %1, %2;" : "=r"(rbar) : "r"(BAR(B_XCH + w)), "r"(kh ^ 1 ^ sc));
#pragma unroll
            for (int g = 0; g < 7; g++) {
                const float v0 = ac[28 + 4 * g + 0], v1 = ac[28 + 4 * g + 1];
                const float v2 = ac[28 + 4 * g + 2], v3 = ac[28 + 4 * g + 3];
                if (!sc) asm volatile("st.async.shared::cluster.mbarrier::complete_tx::bytes.v4.f32 [%0], {%1,%2,%3,%4}, [%5];"
                             ::"r"(rdst + g * 2048), "f"(v0), "f"(v1), "f"(v2), "f"(v3), "r"(rbar) : "memory");
            }
            mbar_wait_cluster(BAR(B_XCH + w), sc);
            PROFC(25);
            bf16* og = (sc ? (bf16*)act : p.out + (size_t)128 * r * DM) + (size_t)ra * DM + 56 * j + 2 * q;
#pragma unroll
            for (int g = 0; g < 7; g++) {
                const uint4 rv = *(const uint4*)(smem + OFF_Y + (5 + w) * 16384 + t * 16 + g * 2048);
                const float2 gb = *(const float2*)(smem + M_G + 224 + (8 * g + 2 * q) * 4);
                const float v0 = ac[4 * g + 0] + __uint_as_float(rv.x), v1 = ac[4 * g + 1] + __uint_as_float(rv.y);
                const float v2 = ac[4 * g + 2] + __uint_as_float(rv.z), v3 = ac[4 * g + 3] + __uint_as_float(rv.w);
                *(uint32_t*)(og + 8 * g) = pack2(fmaf(gb.x, v0, bf_lo(x1p[2 * g])), fmaf(gb.y, v1, bf_hi(x1p[2 * g])));
                *(uint32_t*)(og + 8 * DM + 8 * g) = pack2(fmaf(gb.x, v2, bf_lo(x1p[2 * g + 1])), fmaf(gb.y, v3, bf_hi(x1p[2 * g + 1])));
            }
        }
        PROFC(26);
        bar_sync(1 + w, 128);
        if (wi == 0) warp_arrive(BAR(B_DONE));
    } else {
        const int lane = fresh_tid() & 31;
        const bool early = kh == 0, gemv = r < 14;
        const int mcol = early ? 16 * (4 * r + nq) : 2 * DM + 32 * (4 * r + nq);
        const uint32_t wmbuf = sb + OFF_Y + HALF;
        asm volatile("setmaxnreg.dec.sync.aligned.u32 56;");
        if (warp == 9) {
#pragma unroll
            for (int i = 56; i < 64; i++) init_e(BAR(i), 1);
            fence_async_smem();
        }
        if (warp == 8) { init_e(BAR(B_WMFULL), 1); fence_async_smem(); }
        bar_arrive(0, 384);
        asm volatile("barrier.cluster.arrive.relaxed.aligned;" ::: "memory");
        uint32_t target = 0;
        if (warp == 8) {
            if (!sc) {
                expect_e(BAR(B_WMFULL), gemv ? 28672 >> early : 0);
                if (early && gemv) { tma3_e(wmbuf, &p.wm, mcol, 0, 0, BAR(B_WMFULL)); tma3_e(wmbuf + 7168, &p.wm, mcol, 224, 0, BAR(B_WMFULL)); }
#pragma unroll 1
                for (int kb = 0; kb < 7; kb++) {
                    expect_e(BAR(B_XFULL + kb), 16384);
                    tma3_e(sb + OFF_X + kb * 16384, &p.xm, 64 * kb, 128 * r, 0, BAR(B_XFULL + kb));
                }
            }
#pragma unroll 1
            for (int mt = 0; mt < 4; mt++) {
                if (mt == 1) {
                    if (!early && gemv) {
#pragma unroll 1
                        for (int k = 0; k < 4; k++) tma3_e(wmbuf + k * 7168, &p.wm, mcol + (k >> 1) * 16, (k & 1) * 224, 0, BAR(B_WMFULL));
                    }
                    bar_sync(9, 384);
                    if (sc) return;
                    mbar_wait(BAR(B_MOD1), 0);
                    mbar_wait(BAR(B_WMFREE), 0);
                }
                if (mt == 2) mbar_wait(BAR(B_XFREE), 0);
                if (mt == 3) mbar_wait(BAR(B_VRFULL), 0);
                const uint32_t bar = BAR(mt == 3 ? B_WOFULL : B_FULLK + mt), dst = sb + (mt < 2 ? OFF_Y : OFF_X) + (mt & 1) * HALF;
                const int c0 = (mt < 2 ? DM + DM * mt : 0) + 56 * j - 8 * kh;
                if (!sc) {
                    expect_e(bar, HALF);
                    tma3_e(dst, mt == 3 ? &p.wo : &p.qkv, c0, 0, 0, bar);
                    tma3_e(dst + HALF / 2, mt == 3 ? &p.wo : &p.qkv, c0, 224, 0, bar);
                }
            }
            expect_e(BAR(B_XCH), 14336);
            expect_e(BAR(B_XCH + 1), 14336);
        } else {
            if (warp == 10 && !sc) l2_prefetch_e((const char*)p.wqkv + (size_t)b * 9408, 9408);
            bar_sync(9, 384);
            if (sc) return;
            target = lds1(sb + M_EPOCH) + 1;
            if (warp == 11) {
                const int col = mcol + (early ? lane & 15 : lane);
                mbar_wait(BAR(B_GEMV), 0);
                float sum = 0.f;
#pragma unroll
                for (int i = 0; i < 8; i++) sum += *(const float*)(smem + OFF_Y + HALF + 29696 + (i * 32 + col - mcol) * 4);
                sum = bf_round(sum);
                if ((col >= DM && col < 2 * DM) || (col >= 4 * DM && col < 5 * DM)) sum += 1.f;
                uint32_t* mg = g_mod + col + (early ? (lane >> 4) * 4 * 6 * DM : 0);
#pragma unroll 1
                for (int i = gemv ? (early ? 4 : 8) : 0; i > 0; i--, mg += 6 * DM) st_relaxed(mg, (pack2(sum, 0.f) << 16) | (target & 0xFFFFu));
                warp_arrive(BAR(B_WMFREE));
            }
            if (warp == 9) {
#pragma unroll 1
                for (int kv = 0; kv < 2; kv++) {
                    mbar_wait(BAR(B_PUB + kv), 0);
                    wait_flags(g_flag + b * 128 + lane, target, (r >= 2 ? 6u : r == 1 ? 2u : 0u) << (8 * kv));
                    fence_async_global();
                    const uint32_t dst = sb + OFF_Y + (kv ? Y_VR : Y_K);
                    expect_e(BAR(B_KRFULL + kv), r >= 2 ? 28672 : r == 1 ? 14336 : 0);
                    if (r >= 2) bulk_e(dst, act - 2 * RB_WORDS + RB_KV + j * 7168 + kv * 3584, 14336, BAR(B_KRFULL + kv));
                    if (r >= 1) bulk_e(dst + 14336, act - RB_WORDS + RB_KV + j * 7168 + kv * 3584, 14336, BAR(B_KRFULL + kv));
                }
            } else if (warp == 11) {
                mbar_wait(BAR(B_VRFULL), 0);
                l2_prefetch_e((const char*)p.wg + (size_t)b * 12544, 12544);
                l2_prefetch_e((const char*)p.wu + (size_t)b * 12544, 12544);
#pragma unroll 1
                for (int k = 0; k < (r < 12 ? 2 : 1); k++) {
                    const int u = 28 * kh + r + 16 * k;
                    expect_e(BAR(B_XFULL + k), 7168);
                    tma3_e(sb + OFF_Y + 102400, &p.dn, 0, 32 * u, 7 * j, BAR(B_XFULL + k));
                    tma3_e(sb + OFF_Y + 102400 + 3584, &p.dn, 0, 32 * u, 7 * (j ^ 1), BAR(B_XFULL + k));
                    mbar_wait(BAR(B_XFULL + k), 1);
                    asm volatile("{\n.reg .pred p;\nelect.sync _|p, 0xffffffff;\n@p cp.async.bulk.global.shared::cta.bulk_group [%0], [%1], 7168;\n"
                                 "cp.async.bulk.commit_group;\ncp.async.bulk.wait_group 0;\n}" ::"l"(g_wd + (size_t)(u * 4 + nq) * 1792), "r"(sb + OFF_Y + 102400) : "memory");
                    __syncwarp();
                }
                warp_arrive(BAR(B_WMFREE));
                fence_gpu();
                if (lane < 16) st_relaxed(g_flag + (8 * lane + j) * 128 + 96 + r, target);
            }
        }
        if (warp == 8 || warp == 11) {
            const int sec = warp == 11;
            if (sec) ring_loader<1>(p, sb, r, j, lane); else ring_loader<0>(p, sb, r, j, lane);
            mbar_wait(BAR(B_DONE), 0);
        } else if (warp == 9) {
#pragma unroll
            for (int ev = 0; ev < 4; ev++) { expect_e(BAR(B_GFULL + ev), ev < 2 ? HALF / 2 : 16384 + 4096); expect_e(BAR(B_XFULL + 2 + ev), ev < 2 ? HALF / 2 : HALF - 16384); }
            mbar_wait(BAR(B_PUB + 2), 0);
            const uint32_t* fp = g_flag + b * 128 + 32 + lane;
            const int par = (target - 1) & 1;
#pragma unroll 1
            for (int n = 0, ev = 0; ev < 4; n++) {
                if (ev == 1) { mbar_wait(BAR(B_WMFREE), 1); mbar_wait(BAR(B_PUB + 3), 0); }
                uint32_t ok = __ballot_sync(~0u, (int)(ld_relaxed(fp) - target) >= 0) >> (8 * ev);
                while ((ok & 0xFFu) == 0xFFu) {
                    asm volatile("fence.acquire.gpu;" ::: "memory");
                    fence_async_global();
                    const int tile = (ev & 1) + (ev >> 1) * par * 2;
                    const uint32_t dst = sb + (ev == 0 ? OFF_X : OFF_Y + (ev & 1) * HALF), first = ev < 2 ? HALF / 2 : 16384;
                    const char* src = (const char*)(act + RB_O + ((ev >> 1) * 2 + tile) * 14336);
                    if (ev >= 2) bulk_e(sb + OFF_X + X_STAT + (ev & 1) * 4096, act + RB_ST + tile * 1024, 4096, BAR(B_GFULL + ev));
                    bulk_e(dst, src, first, BAR(B_GFULL + ev));
                    bulk_e(dst + first, src + first, HALF - first, BAR(B_XFULL + 2 + ev));
                    if (ev) PROFH(4 + ev);
                    ev++; ok >>= 8;
                }
                if (n > SPIN_LIMIT) __trap();
            }
            mbar_wait(BAR(B_XFULL + 5), 1);
#pragma unroll 1
            for (int hf = 0; hf < 2; hf++) {
                const int tile = (par ^ 1) * 2 + hf;
                uint4* xz = (uint4*)(act + RB_X1 + tile * 14336 + j * 1792) + lane;
#pragma unroll
                for (int i = 0; i < 14; i++) xz[i * 32] = make_uint4(0, 0, 0, 0);
                ((uint4*)(act + RB_ST + (tile * 8 + j) * 128))[lane] = make_uint4(0, 0, 0, 0);
            }
#pragma unroll 1
            for (int ps = 0; ps < 3; ps++) {
                mbar_wait(BAR(B_PUB + 6 + ps), 0);
                wait_flags(g_flag + b * 128 + 64 + lane, target, (0x55u << kh) << (8 * ps));
                warp_arrive(BAR(B_HRDY + ps));
                PROFH(9 + ps);
            }
        } else {
#pragma unroll 1
            for (int k = 0; k < 9; k++) {
                uint32_t* fp = k < 2 ? g_flag + (b + 8 * lane) * 128 + k * 8 + lane : g_flag + (8 * r + lane) * 128 + 16 + k * 8 + j;
                mbar_wait(BAR(B_PUB + k), 0);
                if (k != 4 && k != 5) fence_gpu();
                if (k < 2 ? (lane == 1 || lane == 2) : lane < 8) st_relaxed(fp, target);
                if (k >= 3 && k <= 5) PROFH(k - 3);
            }
        }
    }
}

#undef act
typedef CUresult (*EncodeFn)(CUtensorMap*, CUtensorMapDataType, cuuint32_t, void*, const cuuint64_t*, const cuuint64_t*, const cuuint32_t*,
                             const cuuint32_t*, CUtensorMapInterleave, CUtensorMapSwizzle, CUtensorMapL2promotion, CUtensorMapFloatOOBfill);

static void make_map(EncodeFn fn, CUtensorMap* m, const void* ptr, uint64_t d0, uint64_t d1, uint64_t d2, uint64_t s1, uint64_t s2,
                     uint32_t b0, uint32_t b1, uint32_t b2, CUtensorMapSwizzle sw) {
    cuuint64_t dims[3] = {d0, d1, d2}, strides[2] = {s1, s2};
    cuuint32_t box[3] = {b0, b1, b2}, es[3] = {1, 1, 1};
    CUresult rc = fn(m, CU_TENSOR_MAP_DATA_TYPE_BFLOAT16, 3, (void*)ptr, dims, strides, box, es, CU_TENSOR_MAP_INTERLEAVE_NONE, sw,
                     CU_TENSOR_MAP_L2_PROMOTION_L2_128B, CU_TENSOR_MAP_FLOAT_OOB_FILL_NONE);
    (void)rc;
}

extern "C" void kernel_launch(void* const* d_in, const int* in_sizes, int n_in, void* d_out, int out_size) {
    (void)in_sizes; (void)n_in; (void)out_size;
    static EncodeFn fn = nullptr;
    static uint32_t* act_base = nullptr;
    if (!fn) {
        cudaDriverEntryPointQueryResult st;
        cudaGetDriverEntryPoint("cuTensorMapEncodeTiled", (void**)&fn, cudaEnableDefault, &st);
        void* a = nullptr;
        cudaGetSymbolAddress(&a, g_act);
        act_base = (uint32_t*)(((uintptr_t)a + 0xFFFFF) & ~(uintptr_t)0xFFFFF);
        cudaFuncSetAttribute(fused_block_kernel, cudaFuncAttributeMaxDynamicSharedMemorySize, SMEM_BYTES);
    }
    Params p;
    p.x = (const bf16*)d_in[0];
    const bf16* wqkv = (const bf16*)d_in[1];
    p.wqkv = wqkv;
    p.wop = (const bf16*)d_in[2];
    p.wg = (const bf16*)d_in[4];
    p.wu = (const bf16*)d_in[5];
    p.wd = (const bf16*)d_in[6];
    p.c = (const bf16*)d_in[7];
    p.wmod = (const bf16*)d_in[8];
    p.out = (bf16*)d_out;
    p.zero = 0;
    p.actb = act_base;
    make_map(fn, &p.wm, p.wmod, 2688, 448, 1, 5376, 5376 * 448, 16, 224, 1, CU_TENSOR_MAP_SWIZZLE_NONE);
    make_map(fn, &p.xm, p.x, 448, 2048, 1, 896, 896 * 2048, 64, 128, 1, CU_TENSOR_MAP_SWIZZLE_128B);
    make_map(fn, &p.qkv, wqkv, 1344, 448, 1, 2688, 2688 * 448, 64, 224, 1, CU_TENSOR_MAP_SWIZZLE_128B);
    make_map(fn, &p.wo, p.wop, 448, 448, 1, 896, 896 * 448, 64, 224, 1, CU_TENSOR_MAP_SWIZZLE_128B);
    make_map(fn, &p.ga, p.wg, 64, 448, 28, 3584, 128, 64, 32, 2, CU_TENSOR_MAP_SWIZZLE_128B);
    make_map(fn, &p.ua, p.wu, 64, 448, 28, 3584, 128, 64, 32, 2, CU_TENSOR_MAP_SWIZZLE_128B);
    make_map(fn, &p.gb, p.wg, 64, 448, 28, 3584, 128, 64, 64, 1, CU_TENSOR_MAP_SWIZZLE_128B);
    make_map(fn, &p.ub, p.wu, 64, 448, 28, 3584, 128, 64, 64, 1, CU_TENSOR_MAP_SWIZZLE_128B);
    make_map(fn, &p.gc, p.wg, 32, 448, 56, 3584, 64, 32, 64, 1, CU_TENSOR_MAP_SWIZZLE_64B);
    make_map(fn, &p.uc, p.wu, 32, 448, 56, 3584, 64, 32, 64, 1, CU_TENSOR_MAP_SWIZZLE_64B);
    make_map(fn, &p.dn, p.wd, 8, 1792, 56, 896, 16, 8, 32, 7, CU_TENSOR_MAP_SWIZZLE_NONE);
    fused_block_kernel<<<GRID, 384, SMEM_BYTES>>>(p);
}
```

```cpp
#include <cuda_runtime.h>
#include <cuda_bf16.h>
#include <cuda.h>
#include <stdint.h>

typedef __nv_bfloat16 bf16;

template<uint64_t CB> __device__ __forceinline__ void wgmma_rs_56(float* d, uint32_t a0, uint32_t a1, uint32_t a2, uint32_t a3, uint32_t db, int sd) {
  asm volatile("{\n.reg .pred p;\n.reg .b64 b;\nsetp.ne.b32 p, %33, 0;\nmov.b64 b, {%32, %34};\n"
    "wgmma.mma_async.sync.aligned.m64n56k16.f32.bf16.bf16 {%0,%1,%2,%3,%4,%5,%6,%7,%8,%9,%10,%11,%12,%13,%14,%15,%16,%17,%18,%19,%20,%21,%22,%23,%24,%25,%26,%27}, {%28,%29,%30,%31}, b, p, 1, 1, 1;\n}\n"
    : "+f"(d[0]),"+f"(d[1]),"+f"(d[2]),"+f"(d[3]),"+f"(d[4]),"+f"(d[5]),"+f"(d[6]),"+f"(d[7]),"+f"(d[8]),"+f"(d[9]),"+f"(d[10]),"+f"(d[11]),"+f"(d[12]),"+f"(d[13]),"+f"(d[14]),"+f"(d[15]),"+f"(d[16]),"+f"(d[17]),"+f"(d[18]),"+f"(d[19]),"+f"(d[20]),"+f"(d[21]),"+f"(d[22]),"+f"(d[23]),"+f"(d[24]),"+f"(d[25]),"+f"(d[26]),"+f"(d[27])
    : "r"(a0), "r"(a1), "r"(a2), "r"(a3), "r"(db), "r"(sd), "n"((uint32_t)(CB >> 32)));
}
template<uint64_t CA, uint64_t CB> __device__ __forceinline__ void wgmma_ss_56(float* d, uint32_t da, uint32_t db, int sd) {
  asm volatile("{\n.reg .pred p;\n.reg .b64 a, b;\nsetp.ne.b32 p, %30, 0;\nmov.b64 a, {%28, %31};\nmov.b64 b, {%29, %32};\n"
    "wgmma.mma_async.sync.aligned.m64n56k16.f32.bf16.bf16 {%0,%1,%2,%3,%4,%5,%6,%7,%8,%9,%10,%11,%12,%13,%14,%15,%16,%17,%18,%19,%20,%21,%22,%23,%24,%25,%26,%27}, a, b, p, 1, 1, 0, 1;\n}\n"
    : "+f"(d[0]),"+f"(d[1]),"+f"(d[2]),"+f"(d[3]),"+f"(d[4]),"+f"(d[5]),"+f"(d[6]),"+f"(d[7]),"+f"(d[8]),"+f"(d[9]),"+f"(d[10]),"+f"(d[11]),"+f"(d[12]),"+f"(d[13]),"+f"(d[14]),"+f"(d[15]),"+f"(d[16]),"+f"(d[17]),"+f"(d[18]),"+f"(d[19]),"+f"(d[20]),"+f"(d[21]),"+f"(d[22]),"+f"(d[23]),"+f"(d[24]),"+f"(d[25]),"+f"(d[26]),"+f"(d[27])
    : "r"(da), "r"(db), "r"(sd), "n"((uint32_t)(CA >> 32)), "n"((uint32_t)(CB >> 32)));
}
template<uint64_t CB> __device__ __forceinline__ void wgmma_rs_256(float* d, uint32_t a0, uint32_t a1, uint32_t a2, uint32_t a3, uint32_t db, int sd) {
  asm volatile("{\n.reg .pred p;\n.reg .b64 b;\nsetp.ne.b32 p, %133, 0;\nmov.b64 b, {%132, %134};\n"
    "wgmma.mma_async.sync.aligned.m64n256k16.f32.bf16.bf16 {%0,%1,%2,%3,%4,%5,%6,%7,%8,%9,%10,%11,%12,%13,%14,%15,%16,%17,%18,%19,%20,%21,%22,%23,%24,%25,%26,%27,%28,%29,%30,%31,%32,%33,%34,%35,%36,%37,%38,%39,%40,%41,%42,%43,%44,%45,%46,%47,%48,%49,%50,%51,%52,%53,%54,%55,%56,%57,%58,%59,%60,%61,%62,%63,%64,%65,%66,%67,%68,%69,%70,%71,%72,%73,%74,%75,%76,%77,%78,%79,%80,%81,%82,%83,%84,%85,%86,%87,%88,%89,%90,%91,%92,%93,%94,%95,%96,%97,%98,%99,%100,%101,%102,%103,%104,%105,%106,%107,%108,%109,%110,%111,%112,%113,%114,%115,%116,%117,%118,%119,%120,%121,%122,%123,%124,%125,%126,%127}, {%128,%129,%130,%131}, b, p, 1, 1, 1;\n}\n"
    : "+f"(d[0]),"+f"(d[1]),"+f"(d[2]),"+f"(d[3]),"+f"(d[4]),"+f"(d[5]),"+f"(d[6]),"+f"(d[7]),"+f"(d[8]),"+f"(d[9]),"+f"(d[10]),"+f"(d[11]),"+f"(d[12]),"+f"(d[13]),"+f"(d[14]),"+f"(d[15]),"+f"(d[16]),"+f"(d[17]),"+f"(d[18]),"+f"(d[19]),"+f"(d[20]),"+f"(d[21]),"+f"(d[22]),"+f"(d[23]),"+f"(d[24]),"+f"(d[25]),"+f"(d[26]),"+f"(d[27]),"+f"(d[28]),"+f"(d[29]),"+f"(d[30]),"+f"(d[31]),"+f"(d[32]),"+f"(d[33]),"+f"(d[34]),"+f"(d[35]),"+f"(d[36]),"+f"(d[37]),"+f"(d[38]),"+f"(d[39]),"+f"(d[40]),"+f"(d[41]),"+f"(d[42]),"+f"(d[43]),"+f"(d[44]),"+f"(d[45]),"+f"(d[46]),"+f"(d[47]),"+f"(d[48]),"+f"(d[49]),"+f"(d[50]),"+f"(d[51]),"+f"(d[52]),"+f"(d[53]),"+f"(d[54]),"+f"(d[55]),"+f"(d[56]),"+f"(d[57]),"+f"(d[58]),"+f"(d[59]),"+f"(d[60]),"+f"(d[61]),"+f"(d[62]),"+f"(d[63]),"+f"(d[64]),"+f"(d[65]),"+f"(d[66]),"+f"(d[67]),"+f"(d[68]),"+f"(d[69]),"+f"(d[70]),"+f"(d[71]),"+f"(d[72]),"+f"(d[73]),"+f"(d[74]),"+f"(d[75]),"+f"(d[76]),"+f"(d[77]),"+f"(d[78]),"+f"(d[79]),"+f"(d[80]),"+f"(d[81]),"+f"(d[82]),"+f"(d[83]),"+f"(d[84]),"+f"(d[85]),"+f"(d[86]),"+f"(d[87]),"+f"(d[88]),"+f"(d[89]),"+f"(d[90]),"+f"(d[91]),"+f"(d[92]),"+f"(d[93]),"+f"(d[94]),"+f"(d[95]),"+f"(d[96]),"+f"(d[97]),"+f"(d[98]),"+f"(d[99]),"+f"(d[100]),"+f"(d[101]),"+f"(d[102]),"+f"(d[103]),"+f"(d[104]),"+f"(d[105]),"+f"(d[106]),"+f"(d[107]),"+f"(d[108]),"+f"(d[109]),"+f"(d[110]),"+f"(d[111]),"+f"(d[112]),"+f"(d[113]),"+f"(d[114]),"+f"(d[115]),"+f"(d[116]),"+f"(d[117]),"+f"(d[118]),"+f"(d[119]),"+f"(d[120]),"+f"(d[121]),"+f"(d[122]),"+f"(d[123]),"+f"(d[124]),"+f"(d[125]),"+f"(d[126]),"+f"(d[127])
    : "r"(a0), "r"(a1), "r"(a2), "r"(a3), "r"(db), "r"(sd), "n"((uint32_t)(CB >> 32)));
}
template<uint64_t CA, uint64_t CB> __device__ __forceinline__ void wgmma_ss_128(float* d, uint32_t da, uint32_t db, int sd) {
  asm volatile("{\n.reg .pred p;\n.reg .b64 a, b;\nsetp.ne.b32 p, %66, 0;\nmov.b64 a, {%64, %67};\nmov.b64 b, {%65, %68};\n"
    "wgmma.mma_async.sync.aligned.m64n128k16.f32.bf16.bf16 {%0,%1,%2,%3,%4,%5,%6,%7,%8,%9,%10,%11,%12,%13,%14,%15,%16,%17,%18,%19,%20,%21,%22,%23,%24,%25,%26,%27,%28,%29,%30,%31,%32,%33,%34,%35,%36,%37,%38,%39,%40,%41,%42,%43,%44,%45,%46,%47,%48,%49,%50,%51,%52,%53,%54,%55,%56,%57,%58,%59,%60,%61,%62,%63}, a, b, p, 1, 1, 0, 1;\n}\n"
    : "+f"(d[0]),"+f"(d[1]),"+f"(d[2]),"+f"(d[3]),"+f"(d[4]),"+f"(d[5]),"+f"(d[6]),"+f"(d[7]),"+f"(d[8]),"+f"(d[9]),"+f"(d[10]),"+f"(d[11]),"+f"(d[12]),"+f"(d[13]),"+f"(d[14]),"+f"(d[15]),"+f"(d[16]),"+f"(d[17]),"+f"(d[18]),"+f"(d[19]),"+f"(d[20]),"+f"(d[21]),"+f"(d[22]),"+f"(d[23]),"+f"(d[24]),"+f"(d[25]),"+f"(d[26]),"+f"(d[27]),"+f"(d[28]),"+f"(d[29]),"+f"(d[30]),"+f"(d[31]),"+f"(d[32]),"+f"(d[33]),"+f"(d[34]),"+f"(d[35]),"+f"(d[36]),"+f"(d[37]),"+f"(d[38]),"+f"(d[39]),"+f"(d[40]),"+f"(d[41]),"+f"(d[42]),"+f"(d[43]),"+f"(d[44]),"+f"(d[45]),"+f"(d[46]),"+f"(d[47]),"+f"(d[48]),"+f"(d[49]),"+f"(d[50]),"+f"(d[51]),"+f"(d[52]),"+f"(d[53]),"+f"(d[54]),"+f"(d[55]),"+f"(d[56]),"+f"(d[57]),"+f"(d[58]),"+f"(d[59]),"+f"(d[60]),"+f"(d[61]),"+f"(d[62]),"+f"(d[63])
    : "r"(da), "r"(db), "r"(sd), "n"((uint32_t)(CA >> 32)), "n"((uint32_t)(CB >> 32)));
}
template<uint64_t CA, uint64_t CB> __device__ __forceinline__ void wgmma_ss_64(float* d, uint32_t da, uint32_t db, int sd) {
  asm volatile("{\n.reg .pred p;\n.reg .b64 a, b;\nsetp.ne.b32 p, %34, 0;\nmov.b64 a, {%32, %35};\nmov.b64 b, {%33, %36};\n"
    "wgmma.mma_async.sync.aligned.m64n64k16.f32.bf16.bf16 {%0,%1,%2,%3,%4,%5,%6,%7,%8,%9,%10,%11,%12,%13,%14,%15,%16,%17,%18,%19,%20,%21,%22,%23,%24,%25,%26,%27,%28,%29,%30,%31}, a, b, p, 1, 1, 0, 1;\n}\n"
    : "+f"(d[0]),"+f"(d[1]),"+f"(d[2]),"+f"(d[3]),"+f"(d[4]),"+f"(d[5]),"+f"(d[6]),"+f"(d[7]),"+f"(d[8]),"+f"(d[9]),"+f"(d[10]),"+f"(d[11]),"+f"(d[12]),"+f"(d[13]),"+f"(d[14]),"+f"(d[15]),"+f"(d[16]),"+f"(d[17]),"+f"(d[18]),"+f"(d[19]),"+f"(d[20]),"+f"(d[21]),"+f"(d[22]),"+f"(d[23]),"+f"(d[24]),"+f"(d[25]),"+f"(d[26]),"+f"(d[27]),"+f"(d[28]),"+f"(d[29]),"+f"(d[30]),"+f"(d[31])
    : "r"(da), "r"(db), "r"(sd), "n"((uint32_t)(CA >> 32)), "n"((uint32_t)(CB >> 32)));
}
template<uint64_t CA, uint64_t CB> __device__ __forceinline__ void wgmma_ss_112(float* d, uint32_t da, uint32_t db, int sd) {
  asm volatile("{\n.reg .pred p;\n.reg .b64 a, b;\nsetp.ne.b32 p, %58, 0;\nmov.b64 a, {%56, %59};\nmov.b64 b, {%57, %60};\n"
    "wgmma.mma_async.sync.aligned.m64n112k16.f32.bf16.bf16 {%0,%1,%2,%3,%4,%5,%6,%7,%8,%9,%10,%11,%12,%13,%14,%15,%16,%17,%18,%19,%20,%21,%22,%23,%24,%25,%26,%27,%28,%29,%30,%31,%32,%33,%34,%35,%36,%37,%38,%39,%40,%41,%42,%43,%44,%45,%46,%47,%48,%49,%50,%51,%52,%53,%54,%55}, a, b, p, 1, 1, 0, 1;\n}\n"
    : "+f"(d[0]),"+f"(d[1]),"+f"(d[2]),"+f"(d[3]),"+f"(d[4]),"+f"(d[5]),"+f"(d[6]),"+f"(d[7]),"+f"(d[8]),"+f"(d[9]),"+f"(d[10]),"+f"(d[11]),"+f"(d[12]),"+f"(d[13]),"+f"(d[14]),"+f"(d[15]),"+f"(d[16]),"+f"(d[17]),"+f"(d[18]),"+f"(d[19]),"+f"(d[20]),"+f"(d[21]),"+f"(d[22]),"+f"(d[23]),"+f"(d[24]),"+f"(d[25]),"+f"(d[26]),"+f"(d[27]),"+f"(d[28]),"+f"(d[29]),"+f"(d[30]),"+f"(d[31]),"+f"(d[32]),"+f"(d[33]),"+f"(d[34]),"+f"(d[35]),"+f"(d[36]),"+f"(d[37]),"+f"(d[38]),"+f"(d[39]),"+f"(d[40]),"+f"(d[41]),"+f"(d[42]),"+f"(d[43]),"+f"(d[44]),"+f"(d[45]),"+f"(d[46]),"+f"(d[47]),"+f"(d[48]),"+f"(d[49]),"+f"(d[50]),"+f"(d[51]),"+f"(d[52]),"+f"(d[53]),"+f"(d[54]),"+f"(d[55])
    : "r"(da), "r"(db), "r"(sd), "n"((uint32_t)(CA >> 32)), "n"((uint32_t)(CB >> 32)));
}
template<uint64_t CB> __device__ __forceinline__ void wgmma_rs_112(float* d, uint32_t a0, uint32_t a1, uint32_t a2, uint32_t a3, uint32_t db, int sd) {
  asm volatile("{\n.reg .pred p;\n.reg .b64 b;\nsetp.ne.b32 p, %61, 0;\nmov.b64 b, {%60, %62};\n"
    "wgmma.mma_async.sync.aligned.m64n112k16.f32.bf16.bf16 {%0,%1,%2,%3,%4,%5,%6,%7,%8,%9,%10,%11,%12,%13,%14,%15,%16,%17,%18,%19,%20,%21,%22,%23,%24,%25,%26,%27,%28,%29,%30,%31,%32,%33,%34,%35,%36,%37,%38,%39,%40,%41,%42,%43,%44,%45,%46,%47,%48,%49,%50,%51,%52,%53,%54,%55}, {%56,%57,%58,%59}, b, p, 1, 1, 1;\n}\n"
    : "+f"(d[0]),"+f"(d[1]),"+f"(d[2]),"+f"(d[3]),"+f"(d[4]),"+f"(d[5]),"+f"(d[6]),"+f"(d[7]),"+f"(d[8]),"+f"(d[9]),"+f"(d[10]),"+f"(d[11]),"+f"(d[12]),"+f"(d[13]),"+f"(d[14]),"+f"(d[15]),"+f"(d[16]),"+f"(d[17]),"+f"(d[18]),"+f"(d[19]),"+f"(d[20]),"+f"(d[21]),"+f"(d[22]),"+f"(d[23]),"+f"(d[24]),"+f"(d[25]),"+f"(d[26]),"+f"(d[27]),"+f"(d[28]),"+f"(d[29]),"+f"(d[30]),"+f"(d[31]),"+f"(d[32]),"+f"(d[33]),"+f"(d[34]),"+f"(d[35]),"+f"(d[36]),"+f"(d[37]),"+f"(d[38]),"+f"(d[39]),"+f"(d[40]),"+f"(d[41]),"+f"(d[42]),"+f"(d[43]),"+f"(d[44]),"+f"(d[45]),"+f"(d[46]),"+f"(d[47]),"+f"(d[48]),"+f"(d[49]),"+f"(d[50]),"+f"(d[51]),"+f"(d[52]),"+f"(d[53]),"+f"(d[54]),"+f"(d[55])
    : "r"(a0), "r"(a1), "r"(a2), "r"(a3), "r"(db), "r"(sd), "n"((uint32_t)(CB >> 32)));
}

constexpr int DM = 448;
constexpr int NCTA = 128;
#define MAPPING 1
#define GRID 132
#define PINGPONG 0
#define WIN 6
#define WIN_END 25
#define UNR_B 1
#define UNR_C 1
constexpr int kB = UNR_B, kC = UNR_C;
#define LIKELY(x) __builtin_expect(!!(x), 1)
#define MAP_S 4
constexpr int SPIN_LIMIT = 1 << 22;

constexpr uint32_t OFF_X = 0, OFF_Y = 114688, OFF_MISC = 229376, SMEM_BYTES = 232448;
constexpr uint32_t Y_VR = 0, Y_K = 28672, Y_KOWN = 57344, Y_VOWN = 71680, Y_Q = 86016;
constexpr uint32_t HALF = 57344;
constexpr uint32_t X_STAT = 49152;
constexpr uint32_t M_BAR = OFF_MISC;
constexpr uint32_t M_ST = OFF_MISC + 512;
constexpr uint32_t M_G = OFF_MISC + 2304;
constexpr uint32_t M_EPOCH = OFF_MISC + 3040;
enum { B_XFULL = 0, B_FULLK = 7, B_FULLV = 8, B_FULLQ, B_KRFULL, B_VRFULL, B_WOFULL, B_XCH, B_MOD1 = 15, B_FULL = 16, B_WMFULL = 30,
       B_EMPTY = 32, B_XFREE = B_EMPTY + 12, B_GEMV, B_PEER,
       B_PUB = 47,
       B_WMFREE = 56, B_HRDY, B_GFULL = B_HRDY + 3, B_DONE = 31, B_DUMMY = B_GEMV };

__device__ uint32_t g_ticket;
__device__ __align__(128) uint32_t g_mod[8 * 6 * DM];
__device__ __align__(128) uint32_t g_flag[144 * 128];
constexpr int RB_WORDS = 262144, RB_KV = 0, RB_O = 57344, RB_X1 = 86016, RB_H2 = 143360, RB_ST = 258048;
__device__ __align__(128) uint32_t g_act[18 * RB_WORDS];
__device__ __align__(128) uint32_t g_wd[56 * 4 * 1792];
#define PROFH(id)
#define PROFH1(id)
#define PROFC(id)

struct alignas(64) Params {
    CUtensorMap wm, xm, qkv, wo, ga, ua, gb, ub, gc, uc, dn;
    const bf16 *x, *c, *wqkv, *wmod, *wg, *wu, *wd, *wop;
    bf16* out;
    uint32_t* actb;
    uint32_t zero;
};

__device__ __forceinline__ void mbar_init(uint32_t bar, int cnt) { asm volatile("mbarrier.init.shared::cta.b64 [%0], %1;" ::"r"(bar), "r"(cnt) : "memory"); }
__device__ __forceinline__ void mbar_expect_tx(uint32_t bar, uint32_t bytes) { asm volatile("mbarrier.arrive.expect_tx.shared::cta.b64 _, [%0], %1;" ::"r"(bar), "r"(bytes) : "memory"); }
__device__ __forceinline__ void mbar_arrive(uint32_t bar) { asm volatile("mbarrier.arrive.shared::cta.b64 _, [%0];" ::"r"(bar) : "memory"); }
__device__ __forceinline__ void mbar_wait(uint32_t bar, uint32_t parity) {
    uint32_t ok; int n = 0;
    do {
        asm volatile("{\n.reg .pred p;\nmbarrier.try_wait.parity.shared::cta.b64 p, [%1], %2;\nselp.u32 %0, 1, 0, p;\n}" : "=r"(ok) : "r"(bar), "r"(parity) : "memory");
        if (++n > SPIN_LIMIT) __trap();
    } while (!ok);
}
__device__ __forceinline__ void mbar_wait_c(uint32_t bar, uint32_t parity) {
    asm volatile("{\n.reg .pred p;\nWL:\nmbarrier.try_wait.parity.shared::cta.b64 p, [%0], %1;\n@!p bra WL;\n}" ::"r"(bar), "r"(parity) : "memory");
}
__device__ __forceinline__ void mbar_wait_cluster(uint32_t bar, uint32_t parity) {
    uint32_t ok; int n = 0;
    do {
        asm volatile("{\n.reg .pred p;\nmbarrier.try_wait.parity.acquire.cluster.shared::cta.b64 p, [%1], %2;\nselp.u32 %0, 1, 0, p;\n}" : "=r"(ok) : "r"(bar), "r"(parity) : "memory");
        if (++n > SPIN_LIMIT) __trap();
    } while (!ok);
}
__device__ __forceinline__ void warp_arrive(uint32_t bar) {
    __syncwarp();
    asm volatile("{\n.reg .pred p;\nelect.sync _|p, 0xffffffff;\n@p mbarrier.arrive.shared::cta.b64 _, [%0];\n}" ::"r"(bar) : "memory");
}
__device__ __forceinline__ int opaque(int v) { return __shfl_sync(~0u, v, 0); }
__device__ __forceinline__ int fresh_tid() { int v; asm volatile("mov.u32 %0, %%tid.x;" : "=r"(v)); return v; }
__device__ __forceinline__ void bar_sync(int id, int n) { asm volatile("bar.sync %0, %1;" ::"r"(id), "r"(n) : "memory"); }
__device__ __forceinline__ void bar_arrive(int id, int n) { asm volatile("bar.arrive %0, %1;" ::"r"(id), "r"(n) : "memory"); }
__device__ __forceinline__ void fence_async_smem() { asm volatile("fence.proxy.async.shared::cta;" ::: "memory"); }
__device__ __forceinline__ void fence_async_global() { asm volatile("fence.proxy.async.global;" ::: "memory"); }
__device__ __forceinline__ void fence_gpu() { asm volatile("fence.release.gpu;" ::: "memory"); }
__device__ __forceinline__ void tma3(uint32_t dst, const CUtensorMap* m, int c0, int c1, int c2, uint32_t bar) {
    asm volatile("cp.async.bulk.tensor.3d.shared::cluster.global.mbarrier::complete_tx::bytes [%0], [%1, {%3, %4, %5}], [%2];"
                 ::"r"(dst), "l"(m), "r"(bar), "r"(c0), "r"(c1), "r"(c2) : "memory");
}
__device__ __forceinline__ void bulk_load(uint32_t dst, const void* src, uint32_t bytes, uint32_t bar) {
    asm volatile("cp.async.bulk.shared::cluster.global.mbarrier::complete_tx::bytes [%0], [%1], %2, [%3];" ::"r"(dst), "l"(src), "r"(bytes), "r"(bar) : "memory");
}
__device__ __forceinline__ void expect_e(uint32_t bar, uint32_t bytes) {
    asm volatile("{\n.reg .pred p;\nelect.sync _|p, 0xffffffff;\n@p mbarrier.arrive.expect_tx.shared::cta.b64 _, [%0], %1;\n}" ::"r"(bar), "r"(bytes) : "memory");
}
__device__ __forceinline__ void tma3_e(uint32_t dst, const CUtensorMap* m, int c0, int c1, int c2, uint32_t bar) {
    asm volatile("{\n.reg .pred p;\nelect.sync _|p, 0xffffffff;\n@p cp.async.bulk.tensor.3d.shared::cluster.global.mbarrier::complete_tx::bytes [%0], [%1, {%3, %4, %5}], [%2];\n}"
                 ::"r"(dst), "l"(m), "r"(bar), "r"(c0), "r"(c1), "r"(c2) : "memory");
}
__device__ __forceinline__ void bulk_e(uint32_t dst, const void* src, uint32_t bytes, uint32_t bar) {
    asm volatile("{\n.reg .pred p;\nelect.sync _|p, 0xffffffff;\n@p cp.async.bulk.shared::cluster.global.mbarrier::complete_tx::bytes [%0], [%1], %2, [%3];\n}"
                 ::"r"(dst), "l"(src), "r"(bytes), "r"(bar) : "memory");
}
__device__ __forceinline__ void init_e(uint32_t bar, int cnt) {
    asm volatile("{\n.reg .pred p;\nelect.sync _|p, 0xffffffff;\n@p mbarrier.init.shared::cta.b64 [%0], %1;\n}" ::"r"(bar), "r"(cnt) : "memory");
}
__device__ __forceinline__ void l2_prefetch_e(const void* src, uint32_t bytes) {
    asm volatile("{\n.reg .pred p;\nelect.sync _|p, 0xffffffff;\n@p cp.async.bulk.prefetch.L2.global [%0], %1;\n}" ::"l"(src), "r"(bytes) : "memory");
}
__device__ __forceinline__ uint32_t ld_relaxed(const uint32_t* p) { uint32_t v; asm volatile("ld.relaxed.gpu.global.u32 %0, [%1];" : "=r"(v) : "l"(p) : "memory"); return v; }
__device__ __forceinline__ void st_relaxed(uint32_t* p, uint32_t v) { asm volatile("st.relaxed.gpu.global.u32 [%0], %1;" ::"l"(p), "r"(v) : "memory"); }
__device__ __forceinline__ uint4 ld_relaxed4(const uint4* p) { uint4 v; asm volatile("ld.relaxed.gpu.global.v4.u32 {%0,%1,%2,%3}, [%4];" : "=r"(v.x), "=r"(v.y), "=r"(v.z), "=r"(v.w) : "l"(p) : "memory"); return v; }
__device__ __forceinline__ void st_relaxed4(uint4* p, uint4 v) { asm volatile("st.relaxed.gpu.global.v4.u32 [%0], {%1,%2,%3,%4};" ::"l"(p), "r"(v.x), "r"(v.y), "r"(v.z), "r"(v.w) : "memory"); }
__device__ __forceinline__ uint4 ldg_nc4(const void* p) { uint4 v; asm volatile("ld.global.nc.L1::no_allocate.v4.u32 {%0,%1,%2,%3}, [%4];" : "=r"(v.x), "=r"(v.y), "=r"(v.z), "=r"(v.w) : "l"(p)); return v; }
__device__ __forceinline__ uint32_t ldg_nc(const void* p) { uint32_t v; asm volatile("ld.global.nc.u32 %0, [%1];" : "=r"(v) : "l"(p)); return v; }
__device__ __forceinline__ uint32_t ld_acquire(const uint32_t* p) { uint32_t v; asm volatile("ld.acquire.gpu.global.u32 %0, [%1];" : "=r"(v) : "l"(p) : "memory"); return v; }
__device__ __forceinline__ uint4 lds4(uint32_t a) { uint4 v; asm volatile("ld.shared.v4.u32 {%0,%1,%2,%3}, [%4];" : "=r"(v.x), "=r"(v.y), "=r"(v.z), "=r"(v.w) : "r"(a) : "memory"); return v; }
__device__ __forceinline__ float2 lds2f(uint32_t a) { float2 v; asm volatile("ld.shared.v2.f32 {%0,%1}, [%2];" : "=f"(v.x), "=f"(v.y) : "r"(a) : "memory"); return v; }
__device__ __forceinline__ uint32_t lds1(uint32_t a) { uint32_t v; asm volatile("ld.shared.u32 %0, [%1];" : "=r"(v) : "r"(a) : "memory"); return v; }
__device__ __forceinline__ void sts4(uint32_t a, uint4 v) { asm volatile("st.shared.v4.u32 [%0], {%1,%2,%3,%4};" ::"r"(a), "r"(v.x), "r"(v.y), "r"(v.z), "r"(v.w) : "memory"); }
__device__ __forceinline__ void sts2(uint32_t a, uint32_t x, uint32_t y) { asm volatile("st.shared.v2.u32 [%0], {%1,%2};" ::"r"(a), "r"(x), "r"(y) : "memory"); }
__device__ __forceinline__ void sts1(uint32_t a, uint32_t v) { asm volatile("st.shared.u32 [%0], %1;" ::"r"(a), "r"(v) : "memory"); }
__device__ __forceinline__ void stsm4(uint32_t a, uint32_t r0, uint32_t r1, uint32_t r2, uint32_t r3) {
    asm volatile("stmatrix.sync.aligned.m8n8.x4.shared.b16 [%0], {%1,%2,%3,%4};" ::"r"(a), "r"(r0), "r"(r1), "r"(r2), "r"(r3));
}
__device__ __forceinline__ uint32_t pack2(float lo, float hi) { uint32_t r; asm("cvt.rn.bf16x2.f32 %0, %1, %2;" : "=r"(r) : "f"(hi), "f"(lo)); return r; }
__device__ __forceinline__ uint32_t pack2_relu(float lo, float hi) { uint32_t r; asm("cvt.rn.relu.bf16x2.f32 %0, %1, %2;" : "=r"(r) : "f"(hi), "f"(lo)); return r; }
__device__ __forceinline__ uint32_t hfma2(uint32_t a, uint32_t b, uint32_t c) { uint32_t r; asm("fma.rn.bf16x2 %0, %1, %2, %3;" : "=r"(r) : "r"(a), "r"(b), "r"(c)); return r; }
__device__ __forceinline__ uint32_t hmul2(uint32_t a, uint32_t b) { uint32_t r; asm("mul.rn.bf16x2 %0, %1, %2;" : "=r"(r) : "r"(a), "r"(b)); return r; }
__device__ __forceinline__ float bf_lo(uint32_t v) { return __uint_as_float(v << 16); }
__device__ __forceinline__ float bf_hi(uint32_t v) { return __uint_as_float(v & 0xFFFF0000u); }
__device__ __forceinline__ float bf_round(float v) { return bf_lo(pack2(v, 0.f)); }
__device__ __forceinline__ float ex2(float x) { float r; asm("ex2.approx.ftz.f32 %0, %1;" : "=f"(r) : "f"(x)); return r; }
__device__ __forceinline__ void mma16816(float* d, uint32_t a0, uint32_t a1, uint32_t a2, uint32_t a3, uint32_t b0, uint32_t b1) {
    asm("mma.sync.aligned.m16n8k16.row.col.f32.bf16.bf16.f32 {%0,%1,%2,%3}, {%4,%5,%6,%7}, {%8,%9}, {%0,%1,%2,%3};"
        : "+f"(d[0]), "+f"(d[1]), "+f"(d[2]), "+f"(d[3]) : "r"(a0), "r"(a1), "r"(a2), "r"(a3), "r"(b0), "r"(b1));
}
__device__ __forceinline__ void mma16816_first(float* d, uint32_t a0, uint32_t a1, uint32_t a2, uint32_t a3, uint32_t b0, uint32_t b1) {
    asm volatile("mma.sync.aligned.m16n8k16.row.col.f32.bf16.bf16.f32 {%0,%1,%2,%3}, {%4,%5,%6,%7}, {%8,%9}, {%10,%10,%10,%10};"
        : "=f"(d[0]), "=f"(d[1]), "=f"(d[2]), "=f"(d[3]) : "r"(a0), "r"(a1), "r"(a2), "r"(a3), "r"(b0), "r"(b1), "f"(0.f));
}
__device__ __forceinline__ void mma16816_v(float* d, uint32_t a0, uint32_t a1, uint32_t a2, uint32_t a3, uint32_t b0, uint32_t b1) {
    asm volatile("mma.sync.aligned.m16n8k16.row.col.f32.bf16.bf16.f32 {%0,%1,%2,%3}, {%4,%5,%6,%7}, {%8,%9}, {%0,%1,%2,%3};"
        : "+f"(d[0]), "+f"(d[1]), "+f"(d[2]), "+f"(d[3]) : "r"(a0), "r"(a1), "r"(a2), "r"(a3), "r"(b0), "r"(b1));
}
__device__ __forceinline__ void mma1688(float* d, uint32_t a0, uint32_t a1, uint32_t b0) {
    asm("mma.sync.aligned.m16n8k8.row.col.f32.bf16.bf16.f32 {%0,%1,%2,%3}, {%4,%5}, {%6}, {%0,%1,%2,%3};"
        : "+f"(d[0]), "+f"(d[1]), "+f"(d[2]), "+f"(d[3]) : "r"(a0), "r"(a1), "r"(b0));
}
__device__ __forceinline__ void ldsm4(uint32_t a, uint32_t* r) {
    asm volatile("ldmatrix.sync.aligned.m8n8.x4.shared.b16 {%0,%1,%2,%3}, [%4];" : "=r"(r[0]), "=r"(r[1]), "=r"(r[2]), "=r"(r[3]) : "r"(a));
}
__device__ __forceinline__ void ldsm4t(uint32_t a, uint32_t* r) {
    asm volatile("ldmatrix.sync.aligned.m8n8.x4.trans.shared.b16 {%0,%1,%2,%3}, [%4];" : "=r"(r[0]), "=r"(r[1]), "=r"(r[2]), "=r"(r[3]) : "r"(a));
}
__device__ __forceinline__ float rcp(float x) { float r; asm("rcp.approx.ftz.f32 %0, %1;" : "=f"(r) : "f"(x)); return r; }
__device__ __forceinline__ uint2 ld_relaxed2(const void* p) { uint2 v; asm volatile("ld.relaxed.gpu.global.v2.u32 {%0,%1}, [%2];" : "=r"(v.x), "=r"(v.y) : "l"(p) : "memory"); return v; }
__device__ __forceinline__ void st_relaxed2(void* p, uint32_t x, uint32_t y) { asm volatile("st.relaxed.gpu.global.v2.u32 [%0], {%1,%2};" ::"l"(p), "r"(max(x, 1u)), "r"(max(y, 1u)) : "memory"); }
__host__ __device__ constexpr uint64_t dconst(uint32_t lbo, uint32_t sbo, uint32_t swz) {
    return ((uint64_t)(lbo >> 4) << 16) | ((uint64_t)(sbo >> 4) << 32) | ((uint64_t)swz << 62);
}
__device__ __forceinline__ uint32_t mkdesc(uint32_t addr, uint64_t c) { return (uint32_t)c | ((addr & 0x3FFFF) >> 4); }
#define WG_FENCE() asm volatile("wgmma.fence.sync.aligned;" ::: "memory")
#define WG_COMMIT() asm volatile("wgmma.commit_group.sync.aligned;" ::: "memory")
#define WG_WAIT(n) asm volatile("wgmma.wait_group.sync.aligned %0;" ::"n"(n) : "memory")
template <int N> __device__ __forceinline__ void reg_fence(float* d) {
#pragma unroll
    for (int i = 0; i < N; i++) asm volatile("" : "+f"(d[i])::"memory");
}
template <int N> __device__ __forceinline__ void reg_def(float* d) {
#pragma unroll
    for (int i = 0; i < N; i++) asm volatile("" : "=f"(d[i]));
}
template <int N> __device__ __forceinline__ void reg_def(uint32_t* d) {
#pragma unroll
    for (int i = 0; i < N; i++) asm volatile("" : "=r"(d[i]));
}
__device__ __forceinline__ bool is_unset(uint4 v) { return min(min(v.x, v.y), min(v.z, v.w)) == 0u; }
__device__ __forceinline__ uint4 nz4(uint32_t a, uint32_t b, uint32_t c, uint32_t d) { return make_uint4(max(a, 1u), max(b, 1u), max(c, 1u), max(d, 1u)); }
__device__ __forceinline__ void wait_flags(const uint32_t* p, uint32_t target, uint32_t mask) {
    int n = 0;
    while (~__ballot_sync(~0u, (int)(ld_relaxed(p) - target) >= 0) & mask) { if (++n > SPIN_LIMIT) __trap(); }
    asm volatile("fence.acquire.gpu;" ::: "memory");
}
__device__ __forceinline__ float silu_bf(uint32_t cbits) {
    const float c = __uint_as_float(cbits << 16);
    return bf_round(__fdividef(c, 1.f + fminf(ex2(-1.4426950408889634f * c), 1e30f)));
}
__device__ __forceinline__ void gemv_part(uint32_t wmbuf, int npanel, int wp, int lane) {
    const uint32_t wa = wmbuf + wp * 512 + (8 * (lane >> 4) + (lane & 7)) * 32 + ((lane >> 3) & 1) * 16;
    uint2 B[4];
#pragma unroll
    for (int i = 0; i < 4; i++) { const float2 v = lds2f(wmbuf + 28672 + (wp + 8 * i) * 32 + (lane & 3) * 8); B[i] = make_uint2(__float_as_uint(v.x), __float_as_uint(v.y)); }
#pragma unroll 1
    for (int pn = 0; pn < npanel; pn++) {
        float d[4] = {};
        uint32_t A[16];
#pragma unroll
        for (int i = 0; i < 4; i++) ldsm4t(wa + pn * 14336 + (i < 3 || wp < 4 ? i : 0) * 4096, A + 4 * i);
#pragma unroll
        for (int i = 0; i < 4; i++) mma16816(d, A[4 * i], A[4 * i + 1], A[4 * i + 2], A[4 * i + 3], B[i].x, B[i].y);
        if ((lane & 3) == 0) {
            sts1(wmbuf + 29696 + (wp * 32 + pn * 16 + (lane >> 2)) * 4, __float_as_uint(d[0]));
            sts1(wmbuf + 29696 + (wp * 32 + pn * 16 + 8 + (lane >> 2)) * 4, __float_as_uint(d[2]));
        }
    }
}
__device__ __forceinline__ const uint4* mod_src(int i, int r, int j, bool p2) {
    i = min(i, p2 ? 251 : 223);
    return (const uint4*)g_mod + (r & 7) * (6 * DM / 4) + (i < 224 ? (p2 ? 336 : 0) + i : (i < 238 ? 14 * j + i : 14 * j + i + 322));
}
__device__ __forceinline__ void mod_store(uint32_t sb, uint4 v, const uint4* src, int i, uint32_t sc) {
    const uint32_t tag = lds1(sb + M_EPOCH) + 1;
    while (__any_sync(~0u, (((v.x ^ tag) | (v.y ^ tag) | (v.z ^ tag) | (v.w ^ tag)) & 0xFFFFu) != 0u) && !sc) v = ld_relaxed4(src);
    if (i < 224) {
        const int isc = i >= 112, c4 = i - 112 * isc;
        const uint32_t a = sb + M_ST + (c4 >> 2) * 64 + (c4 & 1) * 32 + (c4 & 2) * 4 + (isc ? 0 : 4);
        sts1(a, __byte_perm(v.x, v.y, 0x7632));
        sts1(a + 16, __byte_perm(v.z, v.w, 0x7632));
    } else if (i < 252) {
        sts4(sb + M_G + (i - 224) * 16, make_uint4(v.x & 0xFFFF0000u, v.y & 0xFFFF0000u, v.z & 0xFFFF0000u, v.w & 0xFFFF0000u));
    }
}
__device__ __forceinline__ int pass_f(int fs, int ps) { return 224 * fs + ((fs & 1) ? (ps == 0 ? 96 : ps == 1 ? 32 : 0) : (ps == 0 ? 0 : ps == 1 ? 128 : 192)); }
__device__ __forceinline__ constexpr uint32_t slot_off(int l) { return l * 16384; }
__device__ __forceinline__ constexpr int g1_slot(int s) { return s < 3 ? s : s < 6 ? s + 1 : s == 6 ? 3 : s % 7; }
__device__ __noinline__ void x1_fix(const uint32_t* g, uint32_t sa, int s) {
#pragma unroll 1
    for (int k = 4 * s; k < 4 * s + 4;) {
        const uint4 v = ld_relaxed4((const uint4*)(g + k * 256));
        sts4(sa + k * 1024, v);
        k += 2 * __all_sync(~0u, min(min(v.x, v.y), min(v.z, v.w)) != 0u);
    }
    __syncwarp();
}
__device__ __forceinline__ void ln_coeffs(float mean, float msq, uint32_t& r2, uint32_t& n2) {
    const float rs = bf_round(rsqrtf(fmaxf(msq - mean * mean, 0.f) + 1e-5f));
    r2 = pack2(rs, rs);
    n2 = pack2(-mean * rs, -mean * rs);
}

#define LOADW bulk_e(dst, g_wd + (size_t)((f >> 5) * 4 + nq) * 1792, 7168, bar);
template <int sec> __device__ __forceinline__ void ring_loader(const Params& p, uint32_t sb_, int r_, int j_, int lane) {
    const uint32_t sb = opaque(sb_);
    const int r = opaque(r_), j = opaque(j_), nq = j >> 1, fs = 4 * (j & 1) + nq;
    const int fa = pass_f(fs, 0), fb = pass_f(fs, 1), fc = pass_f(fs, 2);
#define BAR(i) (sb + M_BAR + 8 * (i))
#define kh (j & 1)
            int sl = 0;
            mbar_wait(BAR(B_PUB + 2), 0);
            wait_flags(g_flag + (8 * r + j) * 128 + 96 + lane, lds1(sb + M_EPOCH) + 1, 0xFFFFu);
            fence_async_global();
#pragma unroll 1
            for (int s = 0; s < 28; s++) {
                const int ps = s < 14 ? 0 : s < 21 ? 1 : 2;
                const uint32_t half = ps < 2 ? 8192 : 4096;
                const int sp = s >= 3 && s < 7 ? (s == 6 ? 3 : s + 1) : sl;
                mbar_wait(BAR(B_EMPTY + sp), (s >= 7 && s < 14) || s >= 21);
                expect_e(BAR(B_FULL + sp), half);
                tma3_e(sb + slot_off(sp) + sec * half, &p.ga + 2 * ps + sec, 0, ps ? 64 * sl : 32 * s, ps == 0 ? fa >> 6 : ps == 1 ? fb >> 6 : fc >> 5, BAR(B_FULL + sp));
                sl = sl == 6 ? 0 : sl + 1;
            }
            if (!sec) PROFH(3);
#pragma unroll 1
            for (int e = 0; e < 4; e++) {
                const uint32_t dst = sb + slot_off(e) + sec * 8192, bar = BAR(B_FULL + e);
                const int f = (e < 2 ? fa + 64 * e : e == 2 ? fb : fc) + 32 * sec;
                mbar_wait(BAR(B_EMPTY + e), 0);
                expect_e(bar, e == 3 && sec ? 0 : 7168);
                if (!(e == 3 && sec)) { LOADW }
            }
            sl = 4;
            int e = 4;
#pragma unroll 1
            for (int grp = 0; grp < 9; grp++) {
                const int ps = grp >= 6 ? 2 : grp >= 3 ? 1 : 0;
                int sidx = grp - 3 * ps;
                if (sec && sidx == 0) { mbar_wait(BAR(B_HRDY + ps), 0); fence_async_global(); }
                sidx += sidx >= nq;
                int f = pass_f(4 * kh + sidx, ps);
#pragma unroll 1
                for (int k = 4 >> ps; k > 0; k--, e++, f += 32) {
                    const uint32_t dst = sb + slot_off(sl), bar = BAR(B_FULL + sl);
                    mbar_wait(BAR(B_EMPTY + sl), e >= 12 && e < 24);
                    if (e < WIN_END && e >= WIN) mbar_wait(BAR(B_FULL + (sl >= WIN ? sl - WIN : sl + 12 - WIN)), e - WIN >= 12);
                    expect_e(bar, sec ? 8192 : 7168);
                    if (!sec) { LOADW }
                    else bulk_e(dst + 8192, p.actb + (size_t)r * RB_WORDS + RB_H2 + f * 64, 8192, bar);
                    sl = sl == 11 ? 0 : sl + 1;
                }
            }
            if (!sec) PROFH(4);
}

#define act (p.actb + (size_t)r * RB_WORDS)
#define PROF_PARAMS
#define PROF_ARGS
__device__ __noinline__ void helper_late(const Params& p, int r_, int j_, int warp_ PROF_PARAMS) {
    extern __shared__ __align__(1024) unsigned char smem[];
    const uint32_t sb = (uint32_t)__cvta_generic_to_shared(smem);
    const int r = opaque(r_), j = opaque(j_), warp = opaque(warp_), nq = j >> 1, b = 8 * r + j;
    {
        const int lane = fresh_tid() & 31;
        const uint32_t target = lds1(sb + M_EPOCH) + 1;
        if (warp == 8) { expect_e(BAR(B_XCH), 14336); expect_e(BAR(B_XCH + 1), 14336); }
            if (warp == 9) {
#pragma unroll 1
                for (int kv = 0; kv < 2; kv++) {
                    mbar_wait(BAR(B_PUB + kv), 0);
                    wait_flags(g_flag + b * 128 + lane, target, (r >= 2 ? 6u : r == 1 ? 2u : 0u) << (8 * kv));
                    fence_async_global();
                    const uint32_t dst = sb + OFF_Y + (kv ? Y_VR : Y_K);
                    expect_e(BAR(B_KRFULL + kv), r >= 2 ? 28672 : r == 1 ? 14336 : 0);
                    if (r >= 2) bulk_e(dst, act - 2 * RB_WORDS + RB_KV + j * 7168 + kv * 3584, 14336, BAR(B_KRFULL + kv));
                    if (r >= 1) bulk_e(dst + 14336, act - RB_WORDS + RB_KV + j * 7168 + kv * 3584, 14336, BAR(B_KRFULL + kv));
                }
            } else if (warp == 11) {
                mbar_wait(BAR(B_VRFULL), 0);
                l2_prefetch_e((const char*)p.wg + (size_t)b * 12544, 12544);
                l2_prefetch_e((const char*)p.wu + (size_t)b * 12544, 12544);
#pragma unroll 1
                for (int k = 0; k < (r < 12 ? 2 : 1); k++) {
                    const int u = 28 * kh + r + 16 * k;
                    expect_e(BAR(B_XFULL + k), 7168);
                    tma3_e(sb + OFF_Y + 102400, &p.dn, 0, 32 * u, 7 * j, BAR(B_XFULL + k));
                    tma3_e(sb + OFF_Y + 102400 + 3584, &p.dn, 0, 32 * u, 7 * (j ^ 1), BAR(B_XFULL + k));
                    mbar_wait(BAR(B_XFULL + k), 1);
                    asm volatile("{\n.reg .pred p;\nelect.sync _|p, 0xffffffff;\n@p cp.async.bulk.global.shared::cta.bulk_group [%0], [%1], 7168;\n"
                                 "cp.async.bulk.commit_group;\ncp.async.bulk.wait_group 0;\n}" ::"l"(g_wd + (size_t)(u * 4 + nq) * 1792), "r"(sb + OFF_Y + 102400) : "memory");
                    __syncwarp();
                }
                warp_arrive(BAR(B_WMFREE));
                fence_gpu();
                if (lane < 16) st_relaxed(g_flag + (8 * lane + j) * 128 + 96 + r, target);
            }
        if (warp == 8 || warp == 11) {
            const int sec = warp == 11;
            if (sec) ring_loader<1>(p, sb, r, j, lane); else ring_loader<0>(p, sb, r, j, lane);
            mbar_wait(BAR(B_DONE), 0);
        } else if (warp == 9) {
#pragma unroll
            for (int ev = 0; ev < 4; ev++) { expect_e(BAR(B_GFULL + ev), ev < 2 ? HALF / 2 : 16384 + 4096); expect_e(BAR(B_XFULL + 2 + ev), ev < 2 ? HALF / 2 : HALF - 16384); }
            mbar_wait(BAR(B_PUB + 2), 0);
            const uint32_t* fp = g_flag + b * 128 + 32 + lane;
            const int par = (target - 1) & 1;
#pragma unroll 1
            for (int n = 0, ev = 0; ev < 4; n++) {
                if (ev == 1) { mbar_wait(BAR(B_WMFREE), 1); mbar_wait(BAR(B_PUB + 3), 0); }
                uint32_t ok = __ballot_sync(~0u, (int)(ld_relaxed(fp) - target) >= 0) >> (8 * ev);
                while ((ok & 0xFFu) == 0xFFu) {
                    asm volatile("fence.acquire.gpu;" ::: "memory");
                    fence_async_global();
                    const int tile = (ev & 1) + (ev >> 1) * par * 2;
                    const uint32_t dst = sb + (ev == 0 ? OFF_X : OFF_Y + (ev & 1) * HALF), first = ev < 2 ? HALF / 2 : 16384;
                    const char* src = (const char*)(act + RB_O + ((ev >> 1) * 2 + tile) * 14336);
                    if (ev >= 2) bulk_e(sb + OFF_X + X_STAT + (ev & 1) * 4096, act + RB_ST + tile * 1024, 4096, BAR(B_GFULL + ev));
                    bulk_e(dst, src, first, BAR(B_GFULL + ev));
                    bulk_e(dst + first, src + first, HALF - first, BAR(B_XFULL + 2 + ev));
                    if (ev) PROFH(4 + ev);
                    ev++; ok >>= 8;
                }
                if (n > SPIN_LIMIT) __trap();
            }
            mbar_wait(BAR(B_XFULL + 5), 1);
#pragma unroll 1
            for (int hf = 0; hf < 2; hf++) {
                const int tile = (par ^ 1) * 2 + hf;
                uint4* xz = (uint4*)(act + RB_X1 + tile * 14336 + j * 1792) + lane;
#pragma unroll
                for (int i = 0; i < 14; i++) xz[i * 32] = make_uint4(0, 0, 0, 0);
                ((uint4*)(act + RB_ST + (tile * 8 + j) * 128))[lane] = make_uint4(0, 0, 0, 0);
            }
#pragma unroll 1
            for (int ps = 0; ps < 3; ps++) {
                mbar_wait(BAR(B_PUB + 6 + ps), 0);
                wait_flags(g_flag + b * 128 + 64 + lane, target, (0x55u << kh) << (8 * ps));
                warp_arrive(BAR(B_HRDY + ps));
                PROFH(9 + ps);
            }
        } else {
#pragma unroll 1
            for (int k = 0; k < 9; k++) {
                uint32_t* fp = k < 2 ? g_flag + (b + 8 * lane) * 128 + k * 8 + lane : g_flag + (8 * r + lane) * 128 + 16 + k * 8 + j;
                mbar_wait(BAR(B_PUB + k), 0);
                if (k != 4 && k != 5) fence_gpu();
                if (k < 2 ? (lane == 1 || lane == 2) : lane < 8) st_relaxed(fp, target);
                if (k >= 3 && k <= 5) PROFH(k - 3);
            }
        }
    }
}

__global__ void __cluster_dims__(2, 1, 1) __launch_bounds__(384, 1) fused_block_kernel(const __grid_constant__ Params p) {
    extern __shared__ __align__(1024) unsigned char smem[];
    const uint32_t sb = (uint32_t)__cvta_generic_to_shared(smem);
    const int tid = threadIdx.x, lane = tid & 31, warp = __shfl_sync(~0u, tid >> 5, 0);
    const int m = blockIdx.x >> 1;
    int r, nq;
    {
        int g, i;
        if (m < MAP_S) { g = m < 4 ? 15 : 16; i = m & 3; }
        else if (m < MAP_S + 32) { g = (m - MAP_S) & 7; i = (m - MAP_S) >> 3; }
        else if (m < MAP_S + 60) { i = (m - MAP_S - 32) / 7; g = 8 + (m - MAP_S - 32) - 7 * i; }
        else { g = 16; i = m & 3; }
        r = g; nq = i;
    }
    const int j = opaque(2 * nq + (blockIdx.x & 1)), b = 8 * r + j, fs = 4 * kh + nq;
    const uint32_t sc = r == 16;
    if (lane == 0 && warp < 9 && warp != 6 && warp != 7) {
        const int i0 = warp == 8 ? 0 : 8 + 8 * warp, cnt = warp == 0 || warp == 8 ? 1 : warp < 3 ? 2 : 8;
#pragma unroll
        for (int k = 0; k < 8; k++) if (i0 + k != B_WMFULL) mbar_init(BAR(i0 + k), cnt);
        asm volatile("fence.mbarrier_init.release.cluster;" ::: "memory");
        fence_async_smem();
    }

    if (warp >= 8) {
        const int lane = fresh_tid() & 31;
        const bool early = kh == 0, gemv = r < 14;
        const int mcol = early ? 16 * (4 * r + nq) : 2 * DM + 32 * (4 * r + nq);
        const uint32_t wmbuf = sb + OFF_Y + HALF;
        asm volatile("setmaxnreg.dec.sync.aligned.u32 56;");
        if (warp == 9) {
#pragma unroll
            for (int i = 56; i < 64; i++) init_e(BAR(i), 1);
            fence_async_smem();
        }
        if (warp == 8) { init_e(BAR(B_WMFULL), 1); fence_async_smem(); }
        bar_arrive(0, 384);
        asm volatile("barrier.cluster.arrive.relaxed.aligned;" ::: "memory");
        if (warp == 8) {
            if (!sc) {
                expect_e(BAR(B_WMFULL), gemv ? 28672 >> early : 0);
                if (early && gemv) { tma3_e(wmbuf, &p.wm, mcol, 0, 0, BAR(B_WMFULL)); tma3_e(wmbuf + 7168, &p.wm, mcol, 224, 0, BAR(B_WMFULL)); }
#pragma unroll 1
                for (int kb = 0; kb < 7; kb++) {
                    expect_e(BAR(B_XFULL + kb), 16384);
                    tma3_e(sb + OFF_X + kb * 16384, &p.xm, 64 * kb, 128 * r, 0, BAR(B_XFULL + kb));
                }
            }
#pragma unroll 1
            for (int mt = 0; mt < 4; mt++) {
                if (mt == 1) {
                    if (!early && gemv) {
#pragma unroll 1
                        for (int k = 0; k < 4; k++) tma3_e(wmbuf + k * 7168, &p.wm, mcol + (k >> 1) * 16, (k & 1) * 224, 0, BAR(B_WMFULL));
                    }
                    bar_sync(9, 384);
                    if (sc) return;
                    mbar_wait(BAR(B_WMFREE), 0);
                }
                if (mt) mbar_wait(BAR(mt == 1 ? B_MOD1 : mt == 2 ? B_XFREE : B_VRFULL), 0);
                const uint32_t bar = BAR(mt == 3 ? B_WOFULL : B_FULLK + mt), dst = sb + (mt < 2 ? OFF_Y : OFF_X) + (mt & 1) * HALF;
                const int c0 = (mt < 2 ? DM + DM * mt : 0) + 56 * j - 8 * kh;
                if (!sc) {
                    expect_e(bar, HALF);
                    tma3_e(dst, mt == 3 ? &p.wo : &p.qkv, c0, 0, 0, bar);
                    tma3_e(dst + HALF / 2, mt == 3 ? &p.wo : &p.qkv, c0, 224, 0, bar);
                }
            }
        } else {
            if (warp == 10 && !sc) l2_prefetch_e((const char*)p.wqkv + (size_t)b * 9408, 9408);
            bar_sync(9, 384);
            if (sc) return;
            if (warp == 11) {
                const int col = mcol + (early ? lane & 15 : lane);
                const uint32_t tag = (lds1(sb + M_EPOCH) + 1) & 0xFFFFu;
                mbar_wait(BAR(B_GEMV), 0);
                float sum = 0.f;
#pragma unroll
                for (int i = 0; i < 8; i++) sum += *(const float*)(smem + OFF_Y + HALF + 29696 + (i * 32 + col - mcol) * 4);
                sum = bf_round(sum);
                if ((col >= DM && col < 2 * DM) || (col >= 4 * DM && col < 5 * DM)) sum += 1.f;
                uint32_t* mg = g_mod + col + (early ? (lane >> 4) * 4 * 6 * DM : 0);
#pragma unroll 1
                for (int i = gemv ? (early ? 4 : 8) : 0; i > 0; i--, mg += 6 * DM) st_relaxed(mg, (pack2(sum, 0.f) << 16) | tag);
                warp_arrive(BAR(B_WMFREE));
            }
        }
    }
    if (LIKELY(warp < 8)) {
        const int w = warp >> 2, wi = warp & 3;
#define COORDS const int t = fresh_tid() & 127, lane = t & 31, q = lane & 3, lr = lane >> 2, ra = 64 * w + 16 * wi + lr; \
        const uint32_t lx = (lane >> 4) ^ (lane & 7), mrow = (64 * w + 16 * wi + ((lane >> 3) & 1) * 8 + (lane & 7)) * 128; \
        (void)q; (void)lr; (void)ra; (void)lx; (void)mrow;
        const int sid = 2 * (j & 3) + w;
#define RUN(k) (!sc || sid == (k))
#define WAIT(i, par) mbar_wait_c(BAR(i), (par) | sc)
        constexpr uint64_t DB128 = dconst(4096, 1024, 1);
        {
            const int wd = fresh_tid();
            const uint32_t cb = wd < 224 ? __ldg((const uint32_t*)p.c + wd) : 0u;
            if (wd == 255 && !sc) sts1(sb + M_EPOCH, atomicAdd(&g_ticket, 1u) / NCTA);
            sts1(sb + OFF_Y + HALF + 28672 + (wd >> 3) * 32 + (wd & 3) * 8 + (wd & 4), pack2(silu_bf(cb & 0xFFFFu), silu_bf(cb >> 16)));
        }
        bar_arrive(9, 384);
        bar_sync(0, 384);
        asm volatile("barrier.cluster.arrive.relaxed.aligned;" ::: "memory");
        asm volatile("setmaxnreg.inc.sync.aligned.u32 224;");
        PROFC(0);
        uint32_t xr[16];
        {
            COORDS
            uint32_t h[112];
            if (RUN(0)) {
                float ds[4] = {}, da[2][4] = {}, db[2][4] = {};
                const uint32_t ONE2 = 0x3F803F80u;
                if (kh == 0) { WAIT(B_WMFULL, 0); gemv_part(sb + OFF_Y + HALF, 1, warp, lane); warp_arrive(BAR(B_GEMV)); }
#pragma unroll
                for (int kb = 0; kb < 7; kb++) {
                    WAIT(B_XFULL + kb, 0);
#pragma unroll
                    for (int k4 = 0; k4 < 4; k4++) ldsm4(sb + OFF_X + mrow + kb * 16384 + (((2 * k4) ^ lx) << 4), h + 16 * kb + 4 * k4);
#pragma unroll
                    for (int k4 = 0; k4 < 4; k4++) {
                        const uint32_t* f = h + 16 * kb + 4 * k4;
                        mma16816(ds, f[0], f[1], f[2], f[3], ONE2, ONE2);
                        mma1688(da[0], f[0], f[1], f[0]); mma1688(db[0], f[0], f[1], f[1]);
                        mma1688(da[1], f[2], f[3], f[2]); mma1688(db[1], f[2], f[3], f[3]);
                    }
                }
#pragma unroll
                for (int i = 0; i < 4; i++) {
                    const int ch = 7 * j + 2 * i + (lane >> 4);
                    ldsm4(sb + OFF_X + mrow + (ch >> 3) * 16384 + (((ch ^ lane) & 7) << 4), xr + 4 * i);
                }
                warp_arrive(BAR(B_XFREE));
                float qa = (lr & 1) ? da[0][1] + da[1][1] : da[0][0] + da[1][0];
                float qb = (lr & 1) ? db[0][3] + db[1][3] : db[0][2] + db[1][2];
                const int src = (lane & ~3) | (lr >> 1);
                qa = __shfl_sync(~0u, qa, src);
                qb = __shfl_sync(~0u, qb, src);
                uint32_t ra2, na2, rb2, nb2;
                ln_coeffs(ds[0] * (1.f / DM), qa * (1.f / DM), ra2, na2);
                ln_coeffs(ds[2] * (1.f / DM), qb * (1.f / DM), rb2, nb2);
#pragma unroll
                for (int i = 0; i < 112; i += 2) { h[i] = hfma2(h[i], ra2, na2); h[i + 1] = hfma2(h[i + 1], rb2, nb2); }
                if (kh == 1) { WAIT(B_WMFULL, 0); gemv_part(sb + OFF_Y + HALF, 2, warp, lane); warp_arrive(BAR(B_GEMV)); }
            } else { reg_def<112>(h); reg_def<16>(xr); }
            PROFC(1);
            if (RUN(1)) {
                float ak[28], av[28], aq[28];
                uint32_t kp[14], vp[14];
                const uint32_t bk0 = mkdesc(sb + OFF_Y, DB128) + kh, bv0 = mkdesc(sb + OFF_Y + HALF, DB128) + kh, bq0 = mkdesc(sb + OFF_X, DB128) + kh;
                uint32_t* kvg = act + RB_KV + j * 7168 + (8 * w + 2 * wi) * 224 + lane;
                {
                    const int i = min(fresh_tid(), 223);
                    const uint4* src = mod_src(i, r, j, false);
                    mod_store(sb, ld_relaxed4(src), src, i, sc);
                    if (!sc) bar_sync(3, 256);
                    if (warp == 0) warp_arrive(BAR(B_MOD1));
                }
                WAIT(B_FULLK, 0);
                PROFC(2);
                reg_def<28>(ak);
#pragma unroll
                for (int g4 = 0; g4 < 4; g4++) {
#pragma unroll
                    for (int ks = 7 * g4; ks < 7 * g4 + 7; ks++) {
                        const uint4 st = *(const uint4*)(smem + M_ST + ks * 64 + q * 16);
                        h[4 * ks] = hfma2(h[4 * ks], st.x, st.y); h[4 * ks + 1] = hfma2(h[4 * ks + 1], st.x, st.y);
                        h[4 * ks + 2] = hfma2(h[4 * ks + 2], st.z, st.w); h[4 * ks + 3] = hfma2(h[4 * ks + 3], st.z, st.w);
                    }
                    WG_FENCE();
#pragma unroll
                    for (int ks = 7 * g4; ks < 7 * g4 + 7; ks++) wgmma_rs_56<DB128>(ak, h[4 * ks], h[4 * ks + 1], h[4 * ks + 2], h[4 * ks + 3], bk0 + ks * 128, ks != 0);
                }
                WG_COMMIT();
                PROFC(3);
                WAIT(B_FULLV, 0);
                reg_def<28>(av);
                WG_FENCE();
#pragma unroll
                for (int ks = 0; ks < 8; ks++) wgmma_rs_56<DB128>(av, h[4 * ks], h[4 * ks + 1], h[4 * ks + 2], h[4 * ks + 3], bv0 + ks * 128, ks != 0);
                WG_COMMIT();
                WG_WAIT(1);
                reg_fence<28>(ak);
#pragma unroll
                for (int g = 0; g < 7; g++) {
                    kp[2 * g] = pack2(ak[4 * g], ak[4 * g + 1]); kp[2 * g + 1] = pack2(ak[4 * g + 2], ak[4 * g + 3]);
                    kvg[g * 32] = kp[2 * g]; kvg[224 + g * 32] = kp[2 * g + 1];
                }
                warp_arrive(BAR(B_PUB));
                PROFC(4);
                WG_FENCE();
#pragma unroll
                for (int ks = 8; ks < 28; ks++) wgmma_rs_56<DB128>(av, h[4 * ks], h[4 * ks + 1], h[4 * ks + 2], h[4 * ks + 3], bv0 + ks * 128, 1);
                WG_COMMIT();
                WAIT(B_FULLQ, 0);
                reg_def<28>(aq);
                WG_FENCE();
#pragma unroll
                for (int ks = 0; ks < 8; ks++) wgmma_rs_56<DB128>(aq, h[4 * ks], h[4 * ks + 1], h[4 * ks + 2], h[4 * ks + 3], bq0 + ks * 128, ks != 0);
                WG_COMMIT();
                WG_WAIT(1);
                reg_fence<28>(av);
#pragma unroll
                for (int g = 0; g < 7; g++) {
                    vp[2 * g] = pack2(av[4 * g], av[4 * g + 1]); vp[2 * g + 1] = pack2(av[4 * g + 2], av[4 * g + 3]);
                    kvg[3584 + g * 32] = vp[2 * g]; kvg[3584 + 224 + g * 32] = vp[2 * g + 1];
                }
                warp_arrive(BAR(B_PUB + 1));
                const uint4* msrc = mod_src(128 * w + t, r, j, true);
                const uint4 mv = ld_relaxed4(msrc);
                PROFC(5);
                WG_FENCE();
#pragma unroll
                for (int ks = 8; ks < 28; ks++) wgmma_rs_56<DB128>(aq, h[4 * ks], h[4 * ks + 1], h[4 * ks + 2], h[4 * ks + 3], bq0 + ks * 128, 1);
                WG_COMMIT();
                WAIT(B_PUB + 1, 0);
                mod_store(sb, mv, msrc, 128 * w + t, sc);
                const uint32_t ko = sb + OFF_Y + Y_KOWN + (8 * w + 2 * wi) * 896 + lane * 4;
                const uint32_t qo = sb + OFF_Y + Y_Q + (8 * w + 2 * wi) * 1024 + lane * 4;
#pragma unroll
                for (int g = 0; g < 7; g++) {
                    sts1(ko + g * 128, kp[2 * g]); sts1(ko + 896 + g * 128, kp[2 * g + 1]);
                    sts1(ko + (Y_VOWN - Y_KOWN) + g * 128, vp[2 * g]); sts1(ko + (Y_VOWN - Y_KOWN) + 896 + g * 128, vp[2 * g + 1]);
                }
                WG_WAIT(0);
                reg_fence<28>(aq);
                __syncwarp();
                if (lane < 3 && w == 1) mbar_arrive(BAR(B_EMPTY + lane));
#pragma unroll
                for (int g = 0; g < 7; g++) {
                    const uint32_t q0 = pack2(aq[4 * g], aq[4 * g + 1]), q1 = pack2(aq[4 * g + 2], aq[4 * g + 3]);
                    if (g == 3) {
                        sts1(qo + 3 * 128, q < 2 ? q0 : 0u); sts1(qo + 1024 + 3 * 128, q < 2 ? q1 : 0u);
                        sts1(qo + 4 * 128, q < 2 ? 0u : q0); sts1(qo + 1024 + 4 * 128, q < 2 ? 0u : q1);
                    } else {
                        const int ch = g < 3 ? g : g + 1;
                        sts1(qo + ch * 128, q0); sts1(qo + 1024 + ch * 128, q1);
                    }
                }
                if (!sc) bar_sync(3, 256);
            }
        }
        PROFC(6);
        WAIT(B_KRFULL, 0);
        PROFC(7);
        if (RUN(2)) {
#pragma unroll 1
            for (int hf = sc; hf < 2; hf++) {
                COORDS
                float s[136];
                float na = 0.f, nb = 0.f;
                const float CS = 0.18898223650461361f * 1.4426950408889634f;
                const int kg0 = 8 * hf + 2 * wi;
                const int pmin = 16 - 8 * r - 4 * hf - wi;
                const float NEG = __int_as_float(0xFF800000);
                {
                    uint32_t F[8];
                    const uint32_t qa = sb + OFF_Y + Y_Q + (kg0 + ((lane >> 3) & 1)) * 1024 + (4 * w + (lane >> 4)) * 128 + (lane & 7) * 16;
                    ldsm4(qa, F); ldsm4(qa + 256, F + 4);
                    uint32_t ka = sb + OFF_Y + Y_K + kg0 * 896 + (3 * w + (lane >> 3)) * 128 + (lane & 7) * 16;
#pragma unroll
                    for (int g = 0; g < 34; g++) {
                        uint32_t B[4];
                        if (g >= 12 && g % 4 == 0) ka += __float_as_uint(s[4 * (g - 12)]) & p.zero;
                        ldsm4(ka + g * 896, B);
                        mma16816_first(s + 4 * g, F[0], F[1], F[2], F[3], B[0], B[1]);
                        mma16816_v(s + 4 * g, F[4], F[5], F[6], F[7], B[2], B[3]);
                    }
                    const bool c0 = 2 * q > lr, c1 = 2 * q + 1 > lr;
                    if (!c0) { s[0] = NEG; s[6] = NEG; }
                    if (!c1) { s[1] = NEG; s[7] = NEG; }
                    s[2] = NEG; s[3] = NEG;
                    if (c0) { s[128] = NEG; s[134] = NEG; }
                    if (c1) { s[129] = NEG; s[135] = NEG; }
                    s[132] = NEG; s[133] = NEG;
                    float ma = NEG, mb = NEG;
#pragma unroll
                    for (int pp = 0; pp < 17; pp++) {
                        const float* e = s + 8 * pp;
                        const float bias = pp < pmin ? NEG : 0.f;
                        ma = fmaxf(ma, fmaxf(fmaxf(e[0], e[1]), fmaxf(e[4], e[5])) + bias);
                        mb = fmaxf(mb, fmaxf(fmaxf(e[2], e[3]), fmaxf(e[6], e[7])) + bias);
                    }
                    ma = fmaxf(ma, __shfl_xor_sync(~0u, ma, 1)); mb = fmaxf(mb, __shfl_xor_sync(~0u, mb, 1));
                    ma = fmaxf(ma, __shfl_xor_sync(~0u, ma, 2)); mb = fmaxf(mb, __shfl_xor_sync(~0u, mb, 2));
                    na = -ma * CS; nb = -mb * CS;
                }
                PROFC(8 + 3 * hf);
                {
                    WAIT(B_VRFULL, 0);
                    float o[16] = {}, rs[4] = {};
                    uint32_t pk[2];
                    const uint32_t va = sb + OFF_Y + Y_VR + (kg0 + ((lane >> 3) & 1)) * 896 + (3 * w + (lane >> 4)) * 128 + (lane & 7) * 16;
#pragma unroll
                    for (int pp = 0; pp < 17; pp++) {
                        uint32_t B[8];
                        const uint32_t v = va + pp * 1792 + (pp == 16 || (pp >= 9 && kg0 + 2 * pp >= 32) ? Y_VOWN - 32 * 896 : 0);
                        ldsm4t(v, B); ldsm4t(v + 256, B + 4);
                        float e[8];
                        const float bias = __uint_as_float((pp < pmin ? 0xFF800000u : 0u) | ((pp < 2 ? B[0] : pk[pp & 1]) & p.zero));
#pragma unroll
                        for (int i = 0; i < 8; i++) e[i] = ex2(fmaf(s[8 * pp + i], CS, ((i & 2) ? nb : na) + bias));
                        const uint32_t p0 = pack2(e[0], e[1]), p1 = pack2(e[2], e[3]), p2 = pack2(e[4], e[5]), p3 = pack2(e[6], e[7]);
                        pk[pp & 1] = p3;
                        mma16816(rs, p0, p1, p2, p3, 0x3F803F80u, 0x3F803F80u);
#pragma unroll
                        for (int g = 0; g < 4; g++) mma16816(o + 4 * g, p0, p1, p2, p3, B[2 * g], B[2 * g + 1]);
                    }
                    PROFC(9 + 3 * hf);
                    const float ia = rcp(rs[0]), ib = rcp(rs[2]);
                    uint32_t* og = act + RB_O + hf * 14336 + (7 * j + 3 * w) * 256 + wi * 64 + lane;
#pragma unroll
                    for (int g = 0; g < 4; g++) {
                        if ((g == 3 - 3 * w) ? ((q >> 1) == w) : true) {
                            og[g * 256] = pack2(o[4 * g] * ia, o[4 * g + 1] * ia);
                            og[g * 256 + 32] = pack2(o[4 * g + 2] * ib, o[4 * g + 3] * ib);
                        }
                    }
                    warp_arrive(BAR(B_PUB + 2 + hf));
                    PROFC(10 + 3 * hf);
                }
            }
        }
        uint32_t x1p[14];
        COORDS
        constexpr uint64_t DT = dconst(1024, 128, 0);
        const int tile = opaque((lds1(sb + M_EPOCH) & 1) * 2 + w);
        if (RUN(4)) {
            float ac[28];
            const uint32_t ad = mkdesc(sb + (w ? OFF_Y + HALF : OFF_X), DT), bd = mkdesc(sb + OFF_X + HALF, DB128) + kh;
            WAIT(B_WOFULL, 0);
            WAIT(B_GFULL + w, 0);
            PROFC(28);
            reg_def<28>(ac);
#pragma unroll 1
            for (int u = 0; u < 4; u++) {
                if (u == 2) WAIT(B_XFULL + 2 + w, 1);
                WG_FENCE();
#pragma unroll
                for (int i = 0; i < 7; i++) wgmma_ss_56<DT, DB128>(ac, ad + (7 * u + i) * 128, bd + (7 * u + i) * 128, (u | i) != 0);
            }
            WG_COMMIT();
            WG_WAIT(0);
            reg_fence<28>(ac);
            PROFC(14);
            __syncwarp();
            if (lane < 3) mbar_arrive(BAR(B_EMPTY + 4 + lane));
            if (lane < 3 && w == 0) mbar_arrive(BAR(B_EMPTY + lane));
            float s1a = 0.f, s2a = 0.f, s1b = 0.f, s2b = 0.f;
            uint32_t* xo = act + RB_X1 + tile * 14336 + 7 * j * 256 + wi * 64 + lane;
#pragma unroll
            for (int g = 0; g < 7; g++) {
                const float2 ga = *(const float2*)(smem + M_G + (8 * g + 2 * q) * 4);
                x1p[2 * g] = pack2(fmaf(ga.x, ac[4 * g], bf_lo(xr[2 * g])), fmaf(ga.y, ac[4 * g + 1], bf_hi(xr[2 * g])));
                x1p[2 * g + 1] = pack2(fmaf(ga.x, ac[4 * g + 2], bf_lo(xr[2 * g + 1])), fmaf(ga.y, ac[4 * g + 3], bf_hi(xr[2 * g + 1])));
                st_relaxed(xo + g * 256, max(x1p[2 * g], 1u)); st_relaxed(xo + g * 256 + 32, max(x1p[2 * g + 1], 1u));
                const float u0 = bf_lo(x1p[2 * g]), u1 = bf_hi(x1p[2 * g]), u2 = bf_lo(x1p[2 * g + 1]), u3 = bf_hi(x1p[2 * g + 1]);
                s1a += u0 + u1; s2a += u0 * u0 + u1 * u1; s1b += u2 + u3; s2b += u2 * u2 + u3 * u3;
            }
            float ka = (q & 1) ? s2a : s1a, kb2 = (q & 1) ? s2b : s1b;
            ka += __shfl_xor_sync(~0u, (q & 1) ? s1a : s2a, 1); kb2 += __shfl_xor_sync(~0u, (q & 1) ? s1b : s2b, 1);
            const float kk = ((q & 2) ? kb2 : ka) + __shfl_xor_sync(~0u, (q & 2) ? ka : kb2, 2);
            st_relaxed(act + RB_ST + ((tile * 8 + j) * 64 + 16 * wi + lr + 4 * (q & 2)) * 2 + (q & 1), max(__float_as_uint(kk), 1u));
            __syncwarp();
            if (lane < 2) mbar_arrive(BAR(B_PUB + 4 + w));
        } else reg_def<14>(x1p);
        PROFC(15);
        uint32_t h2a[32], h2b[24];
        {
            const int fa = pass_f(fs, 0), fb = pass_f(fs, 1), fc = pass_f(fs, 2);
            uint32_t* h2g = act + RB_H2 + (8 * w + 2 * wi) * 32 + lane;
            const uint32_t a0 = mkdesc(sb + OFF_Y + w * HALF, DT);
            if (RUN(3)) {
                uint32_t ra2, na2, rb2, nb2;
                {
                    const uint32_t* sg = act + RB_ST + ((tile * 8 + 2 * q) * 64 + 16 * wi + lr) * 2;
                    uint2 u[4];
                    WAIT(B_GFULL + 2 + w, 0);
                    PROFC(16);
#pragma unroll
                    for (int i = 0; i < 4; i++) { const float2 v = lds2f(sb + OFF_X + X_STAT + w * 4096 + ((2 * q + (i >> 1)) * 64 + 16 * wi + lr + 8 * (i & 1)) * 8); u[i] = make_uint2(__float_as_uint(v.x), __float_as_uint(v.y)); }
                    while (__any_sync(~0u, min(min(min(u[0].x, u[0].y), min(u[1].x, u[1].y)), min(min(u[2].x, u[2].y), min(u[3].x, u[3].y))) < 1u - sc)) {
#pragma unroll
                        for (int i = 0; i < 4; i++) u[i] = ld_relaxed2(sg + (i >> 1) * 128 + (i & 1) * 16);
                    }
                    warp_arrive(BAR(B_EMPTY + 3));
                    float v[4] = {__uint_as_float(u[0].x) + __uint_as_float(u[2].x), __uint_as_float(u[0].y) + __uint_as_float(u[2].y),
                                  __uint_as_float(u[1].x) + __uint_as_float(u[3].x), __uint_as_float(u[1].y) + __uint_as_float(u[3].y)};
#pragma unroll
                    for (int i = 0; i < 4; i++) { v[i] += __shfl_xor_sync(~0u, v[i], 1); v[i] += __shfl_xor_sync(~0u, v[i], 2); }
                    ln_coeffs(v[0] * (1.f / DM), v[1] * (1.f / DM), ra2, na2);
                    ln_coeffs(v[2] * (1.f / DM), v[3] * (1.f / DM), rb2, nb2);
                }
                const uint32_t ha = sb + OFF_Y + w * HALF + (lane >> 4) * 1024 + (2 * wi + ((lane >> 3) & 1)) * 128 + (lane & 7) * 16;
                const uint32_t sta = sb + M_ST + q * 16;
                const uint32_t* xg = act + RB_X1 + tile * 14336 + (lane >> 4) * 256 + wi * 64 + (lane & 15) * 4;
                uint32_t x[8];
                const uint32_t xs = sb + OFF_Y + w * HALF + (lane >> 4) * 1024 + wi * 256 + (lane & 15) * 16;
                uint4 st[2];
                auto load = [&](int s) {
                    if (s == 4) mbar_wait_c(BAR(B_XFULL + 4 + w), 1);
                    ldsm4(ha + s * 4096, x); ldsm4(ha + s * 4096 + 2048, x + 4);
                    st[0] = lds4(sta + s * 128); st[1] = lds4(sta + s * 128 + 64);
                };
                auto prep = [&](int s, uint32_t* f) {
                    if (__any_sync(~0u, min(min(min(x[0], x[1]), min(x[2], x[3])), min(min(x[4], x[5]), min(x[6], x[7]))) < 1u - sc)) {
                        WG_WAIT(0);
                        x1_fix(xg, xs, s);
                        ldsm4(ha + s * 4096, x); ldsm4(ha + s * 4096 + 2048, x + 4);
                    }
#pragma unroll
                    for (int i = 0; i < 2; i++) {
                        f[4 * i] = hfma2(hfma2(x[4 * i], ra2, na2), st[i].x, st[i].y); f[4 * i + 1] = hfma2(hfma2(x[4 * i + 1], rb2, nb2), st[i].x, st[i].y);
                        f[4 * i + 2] = hfma2(hfma2(x[4 * i + 2], ra2, na2), st[i].z, st[i].w); f[4 * i + 3] = hfma2(hfma2(x[4 * i + 3], rb2, nb2), st[i].z, st[i].w);
                    }
                    if (s < 13) load(s + 1);
                    stsm4(ha + s * 4096, f[0], f[1], f[2], f[3]); stsm4(ha + s * 4096 + 2048, f[4], f[5], f[6], f[7]);
                };
                float ac[128];
                uint32_t fr[3][8];
                const uint32_t bx = mkdesc(sb, DB128);
                reg_def<128>(ac);
                load(0);
                prep(0, fr[0]);
                PROFC(17);
#pragma unroll
                for (int s = 0; s < 14; s++) {
                    const uint32_t* f = fr[s % 3];
                    const uint32_t bd = bx + g1_slot(s) * 1024;
                    WAIT(B_FULL + g1_slot(s), s >= 7);
                    WG_FENCE();
                    wgmma_rs_256<DB128>(ac, f[0], f[1], f[2], f[3], bd, s != 0);
                    wgmma_rs_256<DB128>(ac, f[4], f[5], f[6], f[7], bd + 128, 1);
                    WG_COMMIT();
                    if (s < 13) prep(s + 1, fr[(s + 1) % 3]);
                    if (s > 0) { WG_WAIT(1); warp_arrive(BAR(B_EMPTY + g1_slot(s - 1))); }
                }
                fence_async_smem();
                PROFC(18);
                WG_WAIT(0);
                reg_fence<128>(ac);
                warp_arrive(BAR(B_EMPTY + 6));
#pragma unroll
                for (int g = 0; g < 16; g++) {
                    h2a[2 * g] = hmul2(pack2_relu(ac[4 * g], ac[4 * g + 1]), pack2(ac[64 + 4 * g], ac[64 + 4 * g + 1]));
                    h2a[2 * g + 1] = hmul2(pack2_relu(ac[4 * g + 2], ac[4 * g + 3]), pack2(ac[64 + 4 * g + 2], ac[64 + 4 * g + 3]));
                    h2g[(fa / 8 + g) * 512] = h2a[2 * g]; h2g[(fa / 8 + g) * 512 + 32] = h2a[2 * g + 1];
                }
                warp_arrive(BAR(B_PUB + 6));
                bar_sync(1 + w, 128);
            } else reg_def<32>(h2a);
            PROFC(19);
            if (RUN(5)) {
                float ac[64];
                reg_def<64>(ac);
                const uint32_t bx = mkdesc(sb, dconst(8192, 1024, 1));
#pragma unroll kB
                for (int s = 0; s < 7; s++) {
                    WAIT(B_FULL + s, 0);
                    const uint32_t ad = a0 + s * 512, bd = bx + (slot_off(s) >> 4);
                    WG_FENCE();
#pragma unroll
                    for (int k = 0; k < 4; k++) wgmma_ss_128<DT, DB128>(ac, ad + k * 128, bd + k * 128, (s | k) != 0);
                    WG_COMMIT();
                    if (s > 0) { WG_WAIT(1); warp_arrive(BAR(B_EMPTY + s - 1)); }
                }
                WG_WAIT(0);
                reg_fence<64>(ac);
                warp_arrive(BAR(B_EMPTY + 6));
#pragma unroll
                for (int g = 0; g < 8; g++) {
                    h2b[2 * g] = hmul2(pack2_relu(ac[4 * g], ac[4 * g + 1]), pack2(ac[32 + 4 * g], ac[32 + 4 * g + 1]));
                    h2b[2 * g + 1] = hmul2(pack2_relu(ac[4 * g + 2], ac[4 * g + 3]), pack2(ac[32 + 4 * g + 2], ac[32 + 4 * g + 3]));
                    h2g[(fb / 8 + g) * 512] = h2b[2 * g]; h2g[(fb / 8 + g) * 512 + 32] = h2b[2 * g + 1];
                }
                warp_arrive(BAR(B_PUB + 7));
            } else reg_def<16>(h2b);
            PROFC(27);
            if (RUN(6)) {
                float ac[32];
                reg_def<32>(ac);
                const uint32_t bx = mkdesc(sb, dconst(4096, 512, 2));
#pragma unroll kC
                for (int s = 0; s < 7; s++) {
                    WAIT(B_FULL + s, 1);
                    const uint32_t ad = a0 + s * 512, bd = bx + (slot_off(s) >> 4);
                    WG_FENCE();
#pragma unroll
                    for (int k = 0; k < 4; k++) wgmma_ss_64<DT, dconst(4096, 512, 2)>(ac, ad + k * 128, bd + k * 64, (s | k) != 0);
                    WG_COMMIT();
                    if (s > 0) { WG_WAIT(1); warp_arrive(BAR(B_EMPTY + s - 1)); }
                }
                WG_WAIT(0);
                reg_fence<32>(ac);
                __syncwarp();
                if (lane < 6) mbar_arrive(BAR(B_EMPTY + 6 + lane));
                PROFC(20);
#pragma unroll
                for (int g = 0; g < 4; g++) {
                    h2b[16 + 2 * g] = hmul2(pack2_relu(ac[4 * g], ac[4 * g + 1]), pack2(ac[16 + 4 * g], ac[16 + 4 * g + 1]));
                    h2b[16 + 2 * g + 1] = hmul2(pack2_relu(ac[4 * g + 2], ac[4 * g + 3]), pack2(ac[16 + 4 * g + 2], ac[16 + 4 * g + 3]));
                    h2g[(fc / 8 + g) * 512] = h2b[16 + 2 * g]; h2g[(fc / 8 + g) * 512 + 32] = h2b[16 + 2 * g + 1];
                }
                warp_arrive(BAR(B_PUB + 8));
                asm volatile("barrier.cluster.wait.aligned;" ::: "memory");
                if (lane == 0 && !sc) {
                    uint32_t rb;
                    asm volatile("mapa.shared::cluster.u32 %0, %1, %2;" : "=r"(rb) : "r"(BAR(B_PEER)), "r"(kh ^ 1));
                    asm volatile("mbarrier.arrive.relaxed.cluster.shared::cluster.b64 _, [%0];" ::"r"(rb) : "memory");
                }
            } else reg_def<8>(h2b + 16);
        }
        PROFC(21);
        if (RUN(7)) {
            float ac[56];
            reg_def<56>(ac);
            constexpr uint64_t DAN = dconst(2048, 128, 0);
            constexpr uint64_t DW = dconst(128, 512, 0);
            const uint32_t bx = mkdesc(sb, DW);
#pragma unroll
            for (int e = 0; e < 4; e++) {
                WAIT(B_FULL + e, 0);
                const uint32_t bd = bx + (slot_off(e) >> 4);
                const uint32_t* hh = e < 2 ? h2a + 16 * e : h2b + 16 * (e - 2);
                WG_FENCE();
#pragma unroll
                for (int k = 0; k < (e < 3 ? 4 : 2); k++) wgmma_rs_112<DW>(ac, hh[4 * k], hh[4 * k + 1], hh[4 * k + 2], hh[4 * k + 3], bd + (k >> 1) * 512 + (k & 1) * 16, (e | k) != 0);
                WG_COMMIT();
                if (e > 0) { WG_WAIT(1); warp_arrive(BAR(B_EMPTY + e - 1)); }
            }
            PROFC(22);
            uint32_t ad = mkdesc(sb + 4 * 16384 + 8192 + w * 1024, DAN), bd = bx + 4 * 1024, fb_ = BAR(B_FULL + 4), eb_ = BAR(B_EMPTY + 3), par = sc;
#pragma unroll 1
            for (int e = 4; e < 25; e++) {
                mbar_wait_c(fb_, par);
                WG_FENCE();
                wgmma_ss_112<DAN, DW>(ac, ad, bd, 1);
                wgmma_ss_112<DAN, DW>(ac, ad + 256, bd + 16, 1);
                WG_COMMIT();
                WG_WAIT(1);
                warp_arrive(eb_);
                eb_ = fb_ + 8 * (B_EMPTY - B_FULL);
                ad += 1024; bd += 1024; fb_ += 8;
                if (e == 11 || e == 23) { ad -= 12 * 1024; bd -= 12 * 1024; fb_ -= 96; par = (par ^ 1) | sc; }
            }
            mbar_wait_cluster(BAR(B_PEER), sc);
            WG_WAIT(0);
            reg_fence<56>(ac);
            PROFC(24);
            uint32_t rdst, rbar;
            asm volatile("mapa.shared::cluster.u32 %0, %1, %2;" : "=r"(rdst) : "r"(sb + OFF_Y + (5 + w) * 16384 + t * 16), "r"(kh ^ 1 ^ sc));
            asm volatile("mapa.shared::cluster.u32 %0, %1, %2;" : "=r"(rbar) : "r"(BAR(B_XCH + w)), "r"(kh ^ 1 ^ sc));
#pragma unroll
            for (int g = 0; g < 7; g++) {
                const float v0 = ac[28 + 4 * g + 0], v1 = ac[28 + 4 * g + 1];
                const float v2 = ac[28 + 4 * g + 2], v3 = ac[28 + 4 * g + 3];
                if (!sc) asm volatile("st.async.shared::cluster.mbarrier::complete_tx::bytes.v4.f32 [%0], {%1,%2,%3,%4}, [%5];"
                             ::"r"(rdst + g * 2048), "f"(v0), "f"(v1), "f"(v2), "f"(v3), "r"(rbar) : "memory");
            }
            mbar_wait_cluster(BAR(B_XCH + w), sc);
            PROFC(25);
            bf16* og = (sc ? (bf16*)act : p.out + (size_t)128 * r * DM) + (size_t)ra * DM + 56 * j + 2 * q;
#pragma unroll
            for (int g = 0; g < 7; g++) {
                const uint4 rv = *(const uint4*)(smem + OFF_Y + (5 + w) * 16384 + t * 16 + g * 2048);
                const float2 gb = *(const float2*)(smem + M_G + 224 + (8 * g + 2 * q) * 4);
                const float v0 = ac[4 * g + 0] + __uint_as_float(rv.x), v1 = ac[4 * g + 1] + __uint_as_float(rv.y);
                const float v2 = ac[4 * g + 2] + __uint_as_float(rv.z), v3 = ac[4 * g + 3] + __uint_as_float(rv.w);
                *(uint32_t*)(og + 8 * g) = pack2(fmaf(gb.x, v0, bf_lo(x1p[2 * g])), fmaf(gb.y, v1, bf_hi(x1p[2 * g])));
                *(uint32_t*)(og + 8 * DM + 8 * g) = pack2(fmaf(gb.x, v2, bf_lo(x1p[2 * g + 1])), fmaf(gb.y, v3, bf_hi(x1p[2 * g + 1])));
            }
        }
        PROFC(26);
        bar_sync(1 + w, 128);
        if (wi == 0) warp_arrive(BAR(B_DONE));
        return;
    }
    helper_late(p, r, j, warp PROF_ARGS);
}

#undef act
typedef CUresult (*EncodeFn)(CUtensorMap*, CUtensorMapDataType, cuuint32_t, void*, const cuuint64_t*, const cuuint64_t*, const cuuint32_t*,
                             const cuuint32_t*, CUtensorMapInterleave, CUtensorMapSwizzle, CUtensorMapL2promotion, CUtensorMapFloatOOBfill);

static void make_map(EncodeFn fn, CUtensorMap* m, const void* ptr, uint64_t d0, uint64_t d1, uint64_t d2, uint64_t s1, uint64_t s2,
                     uint32_t b0, uint32_t b1, uint32_t b2, CUtensorMapSwizzle sw) {
    cuuint64_t dims[3] = {d0, d1, d2}, strides[2] = {s1, s2};
    cuuint32_t box[3] = {b0, b1, b2}, es[3] = {1, 1, 1};
    CUresult rc = fn(m, CU_TENSOR_MAP_DATA_TYPE_BFLOAT16, 3, (void*)ptr, dims, strides, box, es, CU_TENSOR_MAP_INTERLEAVE_NONE, sw,
                     CU_TENSOR_MAP_L2_PROMOTION_L2_128B, CU_TENSOR_MAP_FLOAT_OOB_FILL_NONE);
    (void)rc;
}

extern "C" void kernel_launch(void* const* d_in, const int* in_sizes, int n_in, void* d_out, int out_size) {
    (void)in_sizes; (void)n_in; (void)out_size;
    static EncodeFn fn = nullptr;
    static uint32_t* act_base = nullptr;
    if (!fn) {
        cudaDriverEntryPointQueryResult st;
        cudaGetDriverEntryPoint("cuTensorMapEncodeTiled", (void**)&fn, cudaEnableDefault, &st);
        void* a = nullptr;
        cudaGetSymbolAddress(&a, g_act);
        act_base = (uint32_t*)(((uintptr_t)a + 0xFFFFF) & ~(uintptr_t)0xFFFFF);
        cudaFuncSetAttribute(fused_block_kernel, cudaFuncAttributeMaxDynamicSharedMemorySize, SMEM_BYTES);
    }
    Params p;
    p.x = (const bf16*)d_in[0];
    const bf16* wqkv = (const bf16*)d_in[1];
    p.wqkv = wqkv;
    p.wop = (const bf16*)d_in[2];
    p.wg = (const bf16*)d_in[4];
    p.wu = (const bf16*)d_in[5];
    p.wd = (const bf16*)d_in[6];
    p.c = (const bf16*)d_in[7];
    p.wmod = (const bf16*)d_in[8];
    p.out = (bf16*)d_out;
    p.zero = 0;
    p.actb = act_base;
    make_map(fn, &p.wm, p.wmod, 2688, 448, 1, 5376, 5376 * 448, 16, 224, 1, CU_TENSOR_MAP_SWIZZLE_NONE);
    make_map(fn, &p.xm, p.x, 448, 2048, 1, 896, 896 * 2048, 64, 128, 1, CU_TENSOR_MAP_SWIZZLE_128B);
    make_map(fn, &p.qkv, wqkv, 1344, 448, 1, 2688, 2688 * 448, 64, 224, 1, CU_TENSOR_MAP_SWIZZLE_128B);
    make_map(fn, &p.wo, p.wop, 448, 448, 1, 896, 896 * 448, 64, 224, 1, CU_TENSOR_MAP_SWIZZLE_128B);
    make_map(fn, &p.ga, p.wg, 64, 448, 28, 3584, 128, 64, 32, 2, CU_TENSOR_MAP_SWIZZLE_128B);
    make_map(fn, &p.ua, p.wu, 64, 448, 28, 3584, 128, 64, 32, 2, CU_TENSOR_MAP_SWIZZLE_128B);
    make_map(fn, &p.gb, p.wg, 64, 448, 28, 3584, 128, 64, 64, 1, CU_TENSOR_MAP_SWIZZLE_128B);
    make_map(fn, &p.ub, p.wu, 64, 448, 28, 3584, 128, 64, 64, 1, CU_TENSOR_MAP_SWIZZLE_128B);
    make_map(fn, &p.gc, p.wg, 32, 448, 56, 3584, 64, 32, 64, 1, CU_TENSOR_MAP_SWIZZLE_64B);
    make_map(fn, &p.uc, p.wu, 32, 448, 56, 3584, 64, 32, 64, 1, CU_TENSOR_MAP_SWIZZLE_64B);
    make_map(fn, &p.dn, p.wd, 8, 1792, 56, 896, 16, 8, 32, 7, CU_TENSOR_MAP_SWIZZLE_NONE);
    fused_block_kernel<<<GRID, 384, SMEM_BYTES>>>(p);
}
```

```cpp
#include <cuda_runtime.h>
#include <cuda_bf16.h>
#include <cuda.h>
#include <stdint.h>

typedef __nv_bfloat16 bf16;

__device__ __forceinline__ void wgmma_rl_56(float* d, uint32_t a0, uint32_t a1, uint32_t a2, uint32_t a3, uint64_t db, int sd) {
  asm volatile("{\n.reg .pred p;\nsetp.ne.b32 p, %33, 0;\n"
    "wgmma.mma_async.sync.aligned.m64n56k16.f32.bf16.bf16 {%0,%1,%2,%3,%4,%5,%6,%7,%8,%9,%10,%11,%12,%13,%14,%15,%16,%17,%18,%19,%20,%21,%22,%23,%24,%25,%26,%27}, {%28,%29,%30,%31}, %32, p, 1, 1, 1;\n}\n"
    : "+f"(d[0]),"+f"(d[1]),"+f"(d[2]),"+f"(d[3]),"+f"(d[4]),"+f"(d[5]),"+f"(d[6]),"+f"(d[7]),"+f"(d[8]),"+f"(d[9]),"+f"(d[10]),"+f"(d[11]),"+f"(d[12]),"+f"(d[13]),"+f"(d[14]),"+f"(d[15]),"+f"(d[16]),"+f"(d[17]),"+f"(d[18]),"+f"(d[19]),"+f"(d[20]),"+f"(d[21]),"+f"(d[22]),"+f"(d[23]),"+f"(d[24]),"+f"(d[25]),"+f"(d[26]),"+f"(d[27])
    : "r"(a0), "r"(a1), "r"(a2), "r"(a3), "l"(db), "r"(sd));
}
template<uint64_t CA, uint64_t CB> __device__ __forceinline__ void wgmma_ss_56(float* d, uint32_t da, uint32_t db, int sd) {
  asm volatile("{\n.reg .pred p;\n.reg .b64 a, b;\nsetp.ne.b32 p, %30, 0;\nmov.b64 a, {%28, %31};\nmov.b64 b, {%29, %32};\n"
    "wgmma.mma_async.sync.aligned.m64n56k16.f32.bf16.bf16 {%0,%1,%2,%3,%4,%5,%6,%7,%8,%9,%10,%11,%12,%13,%14,%15,%16,%17,%18,%19,%20,%21,%22,%23,%24,%25,%26,%27}, a, b, p, 1, 1, 0, 1;\n}\n"
    : "+f"(d[0]),"+f"(d[1]),"+f"(d[2]),"+f"(d[3]),"+f"(d[4]),"+f"(d[5]),"+f"(d[6]),"+f"(d[7]),"+f"(d[8]),"+f"(d[9]),"+f"(d[10]),"+f"(d[11]),"+f"(d[12]),"+f"(d[13]),"+f"(d[14]),"+f"(d[15]),"+f"(d[16]),"+f"(d[17]),"+f"(d[18]),"+f"(d[19]),"+f"(d[20]),"+f"(d[21]),"+f"(d[22]),"+f"(d[23]),"+f"(d[24]),"+f"(d[25]),"+f"(d[26]),"+f"(d[27])
    : "r"(da), "r"(db), "r"(sd), "n"((uint32_t)(CA >> 32)), "n"((uint32_t)(CB >> 32)));
}
template<uint64_t CB> __device__ __forceinline__ void wgmma_rs_256(float* d, uint32_t a0, uint32_t a1, uint32_t a2, uint32_t a3, uint32_t db, int sd) {
  asm volatile("{\n.reg .pred p;\n.reg .b64 b;\nsetp.ne.b32 p, %133, 0;\nmov.b64 b, {%132, %134};\n"
    "wgmma.mma_async.sync.aligned.m64n256k16.f32.bf16.bf16 {%0,%1,%2,%3,%4,%5,%6,%7,%8,%9,%10,%11,%12,%13,%14,%15,%16,%17,%18,%19,%20,%21,%22,%23,%24,%25,%26,%27,%28,%29,%30,%31,%32,%33,%34,%35,%36,%37,%38,%39,%40,%41,%42,%43,%44,%45,%46,%47,%48,%49,%50,%51,%52,%53,%54,%55,%56,%57,%58,%59,%60,%61,%62,%63,%64,%65,%66,%67,%68,%69,%70,%71,%72,%73,%74,%75,%76,%77,%78,%79,%80,%81,%82,%83,%84,%85,%86,%87,%88,%89,%90,%91,%92,%93,%94,%95,%96,%97,%98,%99,%100,%101,%102,%103,%104,%105,%106,%107,%108,%109,%110,%111,%112,%113,%114,%115,%116,%117,%118,%119,%120,%121,%122,%123,%124,%125,%126,%127}, {%128,%129,%130,%131}, b, p, 1, 1, 1;\n}\n"
    : "+f"(d[0]),"+f"(d[1]),"+f"(d[2]),"+f"(d[3]),"+f"(d[4]),"+f"(d[5]),"+f"(d[6]),"+f"(d[7]),"+f"(d[8]),"+f"(d[9]),"+f"(d[10]),"+f"(d[11]),"+f"(d[12]),"+f"(d[13]),"+f"(d[14]),"+f"(d[15]),"+f"(d[16]),"+f"(d[17]),"+f"(d[18]),"+f"(d[19]),"+f"(d[20]),"+f"(d[21]),"+f"(d[22]),"+f"(d[23]),"+f"(d[24]),"+f"(d[25]),"+f"(d[26]),"+f"(d[27]),"+f"(d[28]),"+f"(d[29]),"+f"(d[30]),"+f"(d[31]),"+f"(d[32]),"+f"(d[33]),"+f"(d[34]),"+f"(d[35]),"+f"(d[36]),"+f"(d[37]),"+f"(d[38]),"+f"(d[39]),"+f"(d[40]),"+f"(d[41]),"+f"(d[42]),"+f"(d[43]),"+f"(d[44]),"+f"(d[45]),"+f"(d[46]),"+f"(d[47]),"+f"(d[48]),"+f"(d[49]),"+f"(d[50]),"+f"(d[51]),"+f"(d[52]),"+f"(d[53]),"+f"(d[54]),"+f"(d[55]),"+f"(d[56]),"+f"(d[57]),"+f"(d[58]),"+f"(d[59]),"+f"(d[60]),"+f"(d[61]),"+f"(d[62]),"+f"(d[63]),"+f"(d[64]),"+f"(d[65]),"+f"(d[66]),"+f"(d[67]),"+f"(d[68]),"+f"(d[69]),"+f"(d[70]),"+f"(d[71]),"+f"(d[72]),"+f"(d[73]),"+f"(d[74]),"+f"(d[75]),"+f"(d[76]),"+f"(d[77]),"+f"(d[78]),"+f"(d[79]),"+f"(d[80]),"+f"(d[81]),"+f"(d[82]),"+f"(d[83]),"+f"(d[84]),"+f"(d[85]),"+f"(d[86]),"+f"(d[87]),"+f"(d[88]),"+f"(d[89]),"+f"(d[90]),"+f"(d[91]),"+f"(d[92]),"+f"(d[93]),"+f"(d[94]),"+f"(d[95]),"+f"(d[96]),"+f"(d[97]),"+f"(d[98]),"+f"(d[99]),"+f"(d[100]),"+f"(d[101]),"+f"(d[102]),"+f"(d[103]),"+f"(d[104]),"+f"(d[105]),"+f"(d[106]),"+f"(d[107]),"+f"(d[108]),"+f"(d[109]),"+f"(d[110]),"+f"(d[111]),"+f"(d[112]),"+f"(d[113]),"+f"(d[114]),"+f"(d[115]),"+f"(d[116]),"+f"(d[117]),"+f"(d[118]),"+f"(d[119]),"+f"(d[120]),"+f"(d[121]),"+f"(d[122]),"+f"(d[123]),"+f"(d[124]),"+f"(d[125]),"+f"(d[126]),"+f"(d[127])
    : "r"(a0), "r"(a1), "r"(a2), "r"(a3), "r"(db), "r"(sd), "n"((uint32_t)(CB >> 32)));
}
template<uint64_t CA, uint64_t CB> __device__ __forceinline__ void wgmma_ss_128(float* d, uint32_t da, uint32_t db, int sd) {
  asm volatile("{\n.reg .pred p;\n.reg .b64 a, b;\nsetp.ne.b32 p, %66, 0;\nmov.b64 a, {%64, %67};\nmov.b64 b, {%65, %68};\n"
    "wgmma.mma_async.sync.aligned.m64n128k16.f32.bf16.bf16 {%0,%1,%2,%3,%4,%5,%6,%7,%8,%9,%10,%11,%12,%13,%14,%15,%16,%17,%18,%19,%20,%21,%22,%23,%24,%25,%26,%27,%28,%29,%30,%31,%32,%33,%34,%35,%36,%37,%38,%39,%40,%41,%42,%43,%44,%45,%46,%47,%48,%49,%50,%51,%52,%53,%54,%55,%56,%57,%58,%59,%60,%61,%62,%63}, a, b, p, 1, 1, 0, 1;\n}\n"
    : "+f"(d[0]),"+f"(d[1]),"+f"(d[2]),"+f"(d[3]),"+f"(d[4]),"+f"(d[5]),"+f"(d[6]),"+f"(d[7]),"+f"(d[8]),"+f"(d[9]),"+f"(d[10]),"+f"(d[11]),"+f"(d[12]),"+f"(d[13]),"+f"(d[14]),"+f"(d[15]),"+f"(d[16]),"+f"(d[17]),"+f"(d[18]),"+f"(d[19]),"+f"(d[20]),"+f"(d[21]),"+f"(d[22]),"+f"(d[23]),"+f"(d[24]),"+f"(d[25]),"+f"(d[26]),"+f"(d[27]),"+f"(d[28]),"+f"(d[29]),"+f"(d[30]),"+f"(d[31]),"+f"(d[32]),"+f"(d[33]),"+f"(d[34]),"+f"(d[35]),"+f"(d[36]),"+f"(d[37]),"+f"(d[38]),"+f"(d[39]),"+f"(d[40]),"+f"(d[41]),"+f"(d[42]),"+f"(d[43]),"+f"(d[44]),"+f"(d[45]),"+f"(d[46]),"+f"(d[47]),"+f"(d[48]),"+f"(d[49]),"+f"(d[50]),"+f"(d[51]),"+f"(d[52]),"+f"(d[53]),"+f"(d[54]),"+f"(d[55]),"+f"(d[56]),"+f"(d[57]),"+f"(d[58]),"+f"(d[59]),"+f"(d[60]),"+f"(d[61]),"+f"(d[62]),"+f"(d[63])
    : "r"(da), "r"(db), "r"(sd), "n"((uint32_t)(CA >> 32)), "n"((uint32_t)(CB >> 32)));
}
template<uint64_t CA, uint64_t CB> __device__ __forceinline__ void wgmma_ss_64(float* d, uint32_t da, uint32_t db, int sd) {
  asm volatile("{\n.reg .pred p;\n.reg .b64 a, b;\nsetp.ne.b32 p, %34, 0;\nmov.b64 a, {%32, %35};\nmov.b64 b, {%33, %36};\n"
    "wgmma.mma_async.sync.aligned.m64n64k16.f32.bf16.bf16 {%0,%1,%2,%3,%4,%5,%6,%7,%8,%9,%10,%11,%12,%13,%14,%15,%16,%17,%18,%19,%20,%21,%22,%23,%24,%25,%26,%27,%28,%29,%30,%31}, a, b, p, 1, 1, 0, 1;\n}\n"
    : "+f"(d[0]),"+f"(d[1]),"+f"(d[2]),"+f"(d[3]),"+f"(d[4]),"+f"(d[5]),"+f"(d[6]),"+f"(d[7]),"+f"(d[8]),"+f"(d[9]),"+f"(d[10]),"+f"(d[11]),"+f"(d[12]),"+f"(d[13]),"+f"(d[14]),"+f"(d[15]),"+f"(d[16]),"+f"(d[17]),"+f"(d[18]),"+f"(d[19]),"+f"(d[20]),"+f"(d[21]),"+f"(d[22]),"+f"(d[23]),"+f"(d[24]),"+f"(d[25]),"+f"(d[26]),"+f"(d[27]),"+f"(d[28]),"+f"(d[29]),"+f"(d[30]),"+f"(d[31])
    : "r"(da), "r"(db), "r"(sd), "n"((uint32_t)(CA >> 32)), "n"((uint32_t)(CB >> 32)));
}
template<uint64_t CA, uint64_t CB> __device__ __forceinline__ void wgmma_ss_112(float* d, uint32_t da, uint32_t db, int sd) {
  asm volatile("{\n.reg .pred p;\n.reg .b64 a, b;\nsetp.ne.b32 p, %58, 0;\nmov.b64 a, {%56, %59};\nmov.b64 b, {%57, %60};\n"
    "wgmma.mma_async.sync.aligned.m64n112k16.f32.bf16.bf16 {%0,%1,%2,%3,%4,%5,%6,%7,%8,%9,%10,%11,%12,%13,%14,%15,%16,%17,%18,%19,%20,%21,%22,%23,%24,%25,%26,%27,%28,%29,%30,%31,%32,%33,%34,%35,%36,%37,%38,%39,%40,%41,%42,%43,%44,%45,%46,%47,%48,%49,%50,%51,%52,%53,%54,%55}, a, b, p, 1, 1, 0, 1;\n}\n"
    : "+f"(d[0]),"+f"(d[1]),"+f"(d[2]),"+f"(d[3]),"+f"(d[4]),"+f"(d[5]),"+f"(d[6]),"+f"(d[7]),"+f"(d[8]),"+f"(d[9]),"+f"(d[10]),"+f"(d[11]),"+f"(d[12]),"+f"(d[13]),"+f"(d[14]),"+f"(d[15]),"+f"(d[16]),"+f"(d[17]),"+f"(d[18]),"+f"(d[19]),"+f"(d[20]),"+f"(d[21]),"+f"(d[22]),"+f"(d[23]),"+f"(d[24]),"+f"(d[25]),"+f"(d[26]),"+f"(d[27]),"+f"(d[28]),"+f"(d[29]),"+f"(d[30]),"+f"(d[31]),"+f"(d[32]),"+f"(d[33]),"+f"(d[34]),"+f"(d[35]),"+f"(d[36]),"+f"(d[37]),"+f"(d[38]),"+f"(d[39]),"+f"(d[40]),"+f"(d[41]),"+f"(d[42]),"+f"(d[43]),"+f"(d[44]),"+f"(d[45]),"+f"(d[46]),"+f"(d[47]),"+f"(d[48]),"+f"(d[49]),"+f"(d[50]),"+f"(d[51]),"+f"(d[52]),"+f"(d[53]),"+f"(d[54]),"+f"(d[55])
    : "r"(da), "r"(db), "r"(sd), "n"((uint32_t)(CA >> 32)), "n"((uint32_t)(CB >> 32)));
}
template<uint64_t CB> __device__ __forceinline__ void wgmma_rs_112(float* d, uint32_t a0, uint32_t a1, uint32_t a2, uint32_t a3, uint32_t db, int sd) {
  asm volatile("{\n.reg .pred p;\n.reg .b64 b;\nsetp.ne.b32 p, %61, 0;\nmov.b64 b, {%60, %62};\n"
    "wgmma.mma_async.sync.aligned.m64n112k16.f32.bf16.bf16 {%0,%1,%2,%3,%4,%5,%6,%7,%8,%9,%10,%11,%12,%13,%14,%15,%16,%17,%18,%19,%20,%21,%22,%23,%24,%25,%26,%27,%28,%29,%30,%31,%32,%33,%34,%35,%36,%37,%38,%39,%40,%41,%42,%43,%44,%45,%46,%47,%48,%49,%50,%51,%52,%53,%54,%55}, {%56,%57,%58,%59}, b, p, 1, 1, 1;\n}\n"
    : "+f"(d[0]),"+f"(d[1]),"+f"(d[2]),"+f"(d[3]),"+f"(d[4]),"+f"(d[5]),"+f"(d[6]),"+f"(d[7]),"+f"(d[8]),"+f"(d[9]),"+f"(d[10]),"+f"(d[11]),"+f"(d[12]),"+f"(d[13]),"+f"(d[14]),"+f"(d[15]),"+f"(d[16]),"+f"(d[17]),"+f"(d[18]),"+f"(d[19]),"+f"(d[20]),"+f"(d[21]),"+f"(d[22]),"+f"(d[23]),"+f"(d[24]),"+f"(d[25]),"+f"(d[26]),"+f"(d[27]),"+f"(d[28]),"+f"(d[29]),"+f"(d[30]),"+f"(d[31]),"+f"(d[32]),"+f"(d[33]),"+f"(d[34]),"+f"(d[35]),"+f"(d[36]),"+f"(d[37]),"+f"(d[38]),"+f"(d[39]),"+f"(d[40]),"+f"(d[41]),"+f"(d[42]),"+f"(d[43]),"+f"(d[44]),"+f"(d[45]),"+f"(d[46]),"+f"(d[47]),"+f"(d[48]),"+f"(d[49]),"+f"(d[50]),"+f"(d[51]),"+f"(d[52]),"+f"(d[53]),"+f"(d[54]),"+f"(d[55])
    : "r"(a0), "r"(a1), "r"(a2), "r"(a3), "r"(db), "r"(sd), "n"((uint32_t)(CB >> 32)));
}

constexpr int DM = 448;
constexpr int NCTA = 128;
#define MAPPING 1
#define GRID 132
#define PINGPONG 0
#define WIN 6
#define WIN_END 25
#define UNR_B 1
#define UNR_C 1
constexpr int kB = UNR_B, kC = UNR_C;
#define LIKELY(x) __builtin_expect(!!(x), 1)
#define MAP_S 4
constexpr int SPIN_LIMIT = 1 << 22;

constexpr uint32_t OFF_X = 0, OFF_Y = 114688, OFF_MISC = 229376, SMEM_BYTES = 232448;
constexpr uint32_t Y_VR = 0, Y_K = 28672, Y_KOWN = 57344, Y_VOWN = 71680, Y_Q = 86016;
constexpr uint32_t HALF = 57344;
constexpr uint32_t X_STAT = 49152;
constexpr uint32_t M_BAR = OFF_MISC;
constexpr uint32_t M_ST = OFF_MISC + 512;
constexpr uint32_t M_G = OFF_MISC + 2304;
constexpr uint32_t M_EPOCH = OFF_MISC + 3040;
enum { B_XFULL = 0, B_FULLK = 7, B_FULLV = 8, B_FULLQ, B_KRFULL, B_VRFULL, B_WOFULL, B_XCH, B_MOD1 = 15, B_FULL = 16, B_WMFULL = 30,
       B_EMPTY = 32, B_XFREE = B_EMPTY + 12, B_GEMV, B_PEER,
       B_PUB = 47,
       B_WMFREE = 56, B_HRDY, B_GFULL = B_HRDY + 3, B_DONE = 31, B_DUMMY = B_GEMV };

__device__ uint32_t g_ticket;
__device__ __align__(128) uint32_t g_mod[8 * 6 * DM];
__device__ __align__(128) uint32_t g_flag[144 * 128];
constexpr int RB_WORDS = 262144, RB_KV = 0, RB_O = 57344, RB_X1 = 86016, RB_H2 = 143360, RB_ST = 258048;
__device__ __align__(128) uint32_t g_act[18 * RB_WORDS];
__device__ __align__(128) uint32_t g_wd[56 * 4 * 1792];
#define PROFH(id)
#define PROFH1(id)
#define PROFC(id)

struct alignas(64) Params {
    CUtensorMap wm, xm, qkv, wo, ga, ua, gb, ub, gc, uc, dn;
    const bf16 *x, *c, *wqkv, *wmod, *wg, *wu, *wd, *wop;
    bf16* out;
    uint32_t* actb;
    uint32_t zero;
};

__device__ __forceinline__ void mbar_init(uint32_t bar, int cnt) { asm volatile("mbarrier.init.shared::cta.b64 [%0], %1;" ::"r"(bar), "r"(cnt) : "memory"); }
__device__ __forceinline__ void mbar_expect_tx(uint32_t bar, uint32_t bytes) { asm volatile("mbarrier.arrive.expect_tx.shared::cta.b64 _, [%0], %1;" ::"r"(bar), "r"(bytes) : "memory"); }
__device__ __forceinline__ void mbar_arrive(uint32_t bar) { asm volatile("mbarrier.arrive.shared::cta.b64 _, [%0];" ::"r"(bar) : "memory"); }
__device__ __forceinline__ void mbar_wait(uint32_t bar, uint32_t parity) {
    uint32_t ok; int n = 0;
    do {
        asm volatile("{\n.reg .pred p;\nmbarrier.try_wait.parity.shared::cta.b64 p, [%1], %2;\nselp.u32 %0, 1, 0, p;\n}" : "=r"(ok) : "r"(bar), "r"(parity) : "memory");
        if (++n > SPIN_LIMIT) __trap();
    } while (!ok);
}
__device__ __forceinline__ void mbar_wait_c(uint32_t bar, uint32_t parity) {
    asm volatile("{\n.reg .pred p;\nWL:\nmbarrier.try_wait.parity.shared::cta.b64 p, [%0], %1;\n@!p bra WL;\n}" ::"r"(bar), "r"(parity) : "memory");
}
__device__ __forceinline__ void mbar_wait_cluster(uint32_t bar, uint32_t parity) {
    uint32_t ok; int n = 0;
    do {
        asm volatile("{\n.reg .pred p;\nmbarrier.try_wait.parity.acquire.cluster.shared::cta.b64 p, [%1], %2;\nselp.u32 %0, 1, 0, p;\n}" : "=r"(ok) : "r"(bar), "r"(parity) : "memory");
        if (++n > SPIN_LIMIT) __trap();
    } while (!ok);
}
__device__ __forceinline__ void warp_arrive(uint32_t bar) {
    __syncwarp();
    asm volatile("{\n.reg .pred p;\nelect.sync _|p, 0xffffffff;\n@p mbarrier.arrive.shared::cta.b64 _, [%0];\n}" ::"r"(bar) : "memory");
}
__device__ __forceinline__ int opaque(int v) { return __shfl_sync(~0u, v, 0); }
__device__ __forceinline__ int fresh_tid() { int v; asm volatile("mov.u32 %0, %%tid.x;" : "=r"(v)); return v; }
__device__ __forceinline__ void bar_sync(int id, int n) { asm volatile("bar.sync %0, %1;" ::"r"(id), "r"(n) : "memory"); }
__device__ __forceinline__ void bar_arrive(int id, int n) { asm volatile("bar.arrive %0, %1;" ::"r"(id), "r"(n) : "memory"); }
__device__ __forceinline__ void fence_async_smem() { asm volatile("fence.proxy.async.shared::cta;" ::: "memory"); }
__device__ __forceinline__ void fence_async_global() { asm volatile("fence.proxy.async.global;" ::: "memory"); }
__device__ __forceinline__ void fence_gpu() { asm volatile("fence.release.gpu;" ::: "memory"); }
__device__ __forceinline__ void tma3(uint32_t dst, const CUtensorMap* m, int c0, int c1, int c2, uint32_t bar) {
    asm volatile("cp.async.bulk.tensor.3d.shared::cluster.global.mbarrier::complete_tx::bytes [%0], [%1, {%3, %4, %5}], [%2];"
                 ::"r"(dst), "l"(m), "r"(bar), "r"(c0), "r"(c1), "r"(c2) : "memory");
}
__device__ __forceinline__ void bulk_load(uint32_t dst, const void* src, uint32_t bytes, uint32_t bar) {
    asm volatile("cp.async.bulk.shared::cluster.global.mbarrier::complete_tx::bytes [%0], [%1], %2, [%3];" ::"r"(dst), "l"(src), "r"(bytes), "r"(bar) : "memory");
}
__device__ __forceinline__ void expect_e(uint32_t bar, uint32_t bytes) {
    asm volatile("{\n.reg .pred p;\nelect.sync _|p, 0xffffffff;\n@p mbarrier.arrive.expect_tx.shared::cta.b64 _, [%0], %1;\n}" ::"r"(bar), "r"(bytes) : "memory");
}
__device__ __forceinline__ void tma3_e(uint32_t dst, const CUtensorMap* m, int c0, int c1, int c2, uint32_t bar) {
    asm volatile("{\n.reg .pred p;\nelect.sync _|p, 0xffffffff;\n@p cp.async.bulk.tensor.3d.shared::cluster.global.mbarrier::complete_tx::bytes [%0], [%1, {%3, %4, %5}], [%2];\n}"
                 ::"r"(dst), "l"(m), "r"(bar), "r"(c0), "r"(c1), "r"(c2) : "memory");
}
__device__ __forceinline__ void bulk_e(uint32_t dst, const void* src, uint32_t bytes, uint32_t bar) {
    asm volatile("{\n.reg .pred p;\nelect.sync _|p, 0xffffffff;\n@p cp.async.bulk.shared::cluster.global.mbarrier::complete_tx::bytes [%0], [%1], %2, [%3];\n}"
                 ::"r"(dst), "l"(src), "r"(bytes), "r"(bar) : "memory");
}
__device__ __forceinline__ void init_e(uint32_t bar, int cnt) {
    asm volatile("{\n.reg .pred p;\nelect.sync _|p, 0xffffffff;\n@p mbarrier.init.shared::cta.b64 [%0], %1;\n}" ::"r"(bar), "r"(cnt) : "memory");
}
__device__ __forceinline__ void l2_prefetch_e(const void* src, uint32_t bytes) {
    asm volatile("{\n.reg .pred p;\nelect.sync _|p, 0xffffffff;\n@p cp.async.bulk.prefetch.L2.global [%0], %1;\n}" ::"l"(src), "r"(bytes) : "memory");
}
__device__ __forceinline__ uint32_t ld_relaxed(const uint32_t* p) { uint32_t v; asm volatile("ld.relaxed.gpu.global.u32 %0, [%1];" : "=r"(v) : "l"(p) : "memory"); return v; }
__device__ __forceinline__ void st_relaxed(uint32_t* p, uint32_t v) { asm volatile("st.relaxed.gpu.global.u32 [%0], %1;" ::"l"(p), "r"(v) : "memory"); }
__device__ __forceinline__ uint4 ld_relaxed4(const uint4* p) { uint4 v; asm volatile("ld.relaxed.gpu.global.v4.u32 {%0,%1,%2,%3}, [%4];" : "=r"(v.x), "=r"(v.y), "=r"(v.z), "=r"(v.w) : "l"(p) : "memory"); return v; }
__device__ __forceinline__ void st_relaxed4(uint4* p, uint4 v) { asm volatile("st.relaxed.gpu.global.v4.u32 [%0], {%1,%2,%3,%4};" ::"l"(p), "r"(v.x), "r"(v.y), "r"(v.z), "r"(v.w) : "memory"); }
__device__ __forceinline__ uint4 ldg_nc4(const void* p) { uint4 v; asm volatile("ld.global.nc.L1::no_allocate.v4.u32 {%0,%1,%2,%3}, [%4];" : "=r"(v.x), "=r"(v.y), "=r"(v.z), "=r"(v.w) : "l"(p)); return v; }
__device__ __forceinline__ uint32_t ldg_nc(const void* p) { uint32_t v; asm volatile("ld.global.nc.u32 %0, [%1];" : "=r"(v) : "l"(p)); return v; }
__device__ __forceinline__ uint32_t ld_acquire(const uint32_t* p) { uint32_t v; asm volatile("ld.acquire.gpu.global.u32 %0, [%1];" : "=r"(v) : "l"(p) : "memory"); return v; }
__device__ __forceinline__ uint4 lds4(uint32_t a) { uint4 v; asm volatile("ld.shared.v4.u32 {%0,%1,%2,%3}, [%4];" : "=r"(v.x), "=r"(v.y), "=r"(v.z), "=r"(v.w) : "r"(a) : "memory"); return v; }
__device__ __forceinline__ float2 lds2f(uint32_t a) { float2 v; asm volatile("ld.shared.v2.f32 {%0,%1}, [%2];" : "=f"(v.x), "=f"(v.y) : "r"(a) : "memory"); return v; }
__device__ __forceinline__ uint32_t lds1(uint32_t a) { uint32_t v; asm volatile("ld.shared.u32 %0, [%1];" : "=r"(v) : "r"(a) : "memory"); return v; }
__device__ __forceinline__ void sts4(uint32_t a, uint4 v) { asm volatile("st.shared.v4.u32 [%0], {%1,%2,%3,%4};" ::"r"(a), "r"(v.x), "r"(v.y), "r"(v.z), "r"(v.w) : "memory"); }
__device__ __forceinline__ void sts2(uint32_t a, uint32_t x, uint32_t y) { asm volatile("st.shared.v2.u32 [%0], {%1,%2};" ::"r"(a), "r"(x), "r"(y) : "memory"); }
__device__ __forceinline__ void sts1(uint32_t a, uint32_t v) { asm volatile("st.shared.u32 [%0], %1;" ::"r"(a), "r"(v) : "memory"); }
__device__ __forceinline__ void stsm4(uint32_t a, uint32_t r0, uint32_t r1, uint32_t r2, uint32_t r3) {
    asm volatile("stmatrix.sync.aligned.m8n8.x4.shared.b16 [%0], {%1,%2,%3,%4};" ::"r"(a), "r"(r0), "r"(r1), "r"(r2), "r"(r3));
}
__device__ __forceinline__ uint32_t pack2(float lo, float hi) { uint32_t r; asm("cvt.rn.bf16x2.f32 %0, %1, %2;" : "=r"(r) : "f"(hi), "f"(lo)); return r; }
__device__ __forceinline__ uint32_t pack2_relu(float lo, float hi) { uint32_t r; asm("cvt.rn.relu.bf16x2.f32 %0, %1, %2;" : "=r"(r) : "f"(hi), "f"(lo)); return r; }
__device__ __forceinline__ uint32_t hfma2(uint32_t a, uint32_t b, uint32_t c) { uint32_t r; asm("fma.rn.bf16x2 %0, %1, %2, %3;" : "=r"(r) : "r"(a), "r"(b), "r"(c)); return r; }
__device__ __forceinline__ uint32_t hmul2(uint32_t a, uint32_t b) { uint32_t r; asm("mul.rn.bf16x2 %0, %1, %2;" : "=r"(r) : "r"(a), "r"(b)); return r; }
__device__ __forceinline__ float bf_lo(uint32_t v) { return __uint_as_float(v << 16); }
__device__ __forceinline__ float bf_hi(uint32_t v) { return __uint_as_float(v & 0xFFFF0000u); }
__device__ __forceinline__ float bf_round(float v) { return bf_lo(pack2(v, 0.f)); }
__device__ __forceinline__ float ex2(float x) { float r; asm("ex2.approx.ftz.f32 %0, %1;" : "=f"(r) : "f"(x)); return r; }
__device__ __forceinline__ void mma16816(float* d, uint32_t a0, uint32_t a1, uint32_t a2, uint32_t a3, uint32_t b0, uint32_t b1) {
    asm("mma.sync.aligned.m16n8k16.row.col.f32.bf16.bf16.f32 {%0,%1,%2,%3}, {%4,%5,%6,%7}, {%8,%9}, {%0,%1,%2,%3};"
        : "+f"(d[0]), "+f"(d[1]), "+f"(d[2]), "+f"(d[3]) : "r"(a0), "r"(a1), "r"(a2), "r"(a3), "r"(b0), "r"(b1));
}
__device__ __forceinline__ void mma16816_first(float* d, uint32_t a0, uint32_t a1, uint32_t a2, uint32_t a3, uint32_t b0, uint32_t b1) {
    asm volatile("mma.sync.aligned.m16n8k16.row.col.f32.bf16.bf16.f32 {%0,%1,%2,%3}, {%4,%5,%6,%7}, {%8,%9}, {%10,%10,%10,%10};"
        : "=f"(d[0]), "=f"(d[1]), "=f"(d[2]), "=f"(d[3]) : "r"(a0), "r"(a1), "r"(a2), "r"(a3), "r"(b0), "r"(b1), "f"(0.f));
}
__device__ __forceinline__ void mma16816_v(float* d, uint32_t a0, uint32_t a1, uint32_t a2, uint32_t a3, uint32_t b0, uint32_t b1) {
    asm volatile("mma.sync.aligned.m16n8k16.row.col.f32.bf16.bf16.f32 {%0,%1,%2,%3}, {%4,%5,%6,%7}, {%8,%9}, {%0,%1,%2,%3};"
        : "+f"(d[0]), "+f"(d[1]), "+f"(d[2]), "+f"(d[3]) : "r"(a0), "r"(a1), "r"(a2), "r"(a3), "r"(b0), "r"(b1));
}
__device__ __forceinline__ void mma1688(float* d, uint32_t a0, uint32_t a1, uint32_t b0) {
    asm("mma.sync.aligned.m16n8k8.row.col.f32.bf16.bf16.f32 {%0,%1,%2,%3}, {%4,%5}, {%6}, {%0,%1,%2,%3};"
        : "+f"(d[0]), "+f"(d[1]), "+f"(d[2]), "+f"(d[3]) : "r"(a0), "r"(a1), "r"(b0));
}
__device__ __forceinline__ void ldsm4(uint32_t a, uint32_t* r) {
    asm volatile("ldmatrix.sync.aligned.m8n8.x4.shared.b16 {%0,%1,%2,%3}, [%4];" : "=r"(r[0]), "=r"(r[1]), "=r"(r[2]), "=r"(r[3]) : "r"(a));
}
__device__ __forceinline__ void ldsm4t(uint32_t a, uint32_t* r) {
    asm volatile("ldmatrix.sync.aligned.m8n8.x4.trans.shared.b16 {%0,%1,%2,%3}, [%4];" : "=r"(r[0]), "=r"(r[1]), "=r"(r[2]), "=r"(r[3]) : "r"(a));
}
__device__ __forceinline__ uint32_t nz(uint32_t v) { uint32_t r; asm("max.u32 %0, %1, 1;" : "=r"(r) : "r"(v)); return r; }
__device__ __forceinline__ float rcp(float x) { float r; asm("rcp.approx.ftz.f32 %0, %1;" : "=f"(r) : "f"(x)); return r; }
__device__ __forceinline__ uint2 ld_relaxed2(const void* p) { uint2 v; asm volatile("ld.relaxed.gpu.global.v2.u32 {%0,%1}, [%2];" : "=r"(v.x), "=r"(v.y) : "l"(p) : "memory"); return v; }
__device__ __forceinline__ void st_relaxed2(void* p, uint32_t x, uint32_t y) { asm volatile("st.relaxed.gpu.global.v2.u32 [%0], {%1,%2};" ::"l"(p), "r"(max(x, 1u)), "r"(max(y, 1u)) : "memory"); }
__host__ __device__ constexpr uint64_t dconst(uint32_t lbo, uint32_t sbo, uint32_t swz) {
    return ((uint64_t)(lbo >> 4) << 16) | ((uint64_t)(sbo >> 4) << 32) | ((uint64_t)swz << 62);
}
__device__ __forceinline__ uint32_t mkdesc(uint32_t addr, uint64_t c) { return (uint32_t)c | ((addr & 0x3FFFF) >> 4); }
#define WG_FENCE() asm volatile("wgmma.fence.sync.aligned;" ::: "memory")
#define WG_COMMIT() asm volatile("wgmma.commit_group.sync.aligned;" ::: "memory")
#define WG_WAIT(n) asm volatile("wgmma.wait_group.sync.aligned %0;" ::"n"(n) : "memory")
template <int N> __device__ __forceinline__ void reg_fence(float* d) {
#pragma unroll
    for (int i = 0; i < N; i++) asm volatile("" : "+f"(d[i])::"memory");
}
template <int N> __device__ __forceinline__ void reg_def(float* d) {
#pragma unroll
    for (int i = 0; i < N; i++) asm volatile("" : "=f"(d[i]));
}
template <int N> __device__ __forceinline__ void reg_def(uint32_t* d) {
#pragma unroll
    for (int i = 0; i < N; i++) asm volatile("" : "=r"(d[i]));
}
__device__ __forceinline__ bool is_unset(uint4 v) { return min(min(v.x, v.y), min(v.z, v.w)) == 0u; }
__device__ __forceinline__ uint4 nz4(uint32_t a, uint32_t b, uint32_t c, uint32_t d) { return make_uint4(max(a, 1u), max(b, 1u), max(c, 1u), max(d, 1u)); }
__device__ __forceinline__ void wait_flags(const uint32_t* p, uint32_t target, uint32_t mask) {
    int n = 0;
    while (~__ballot_sync(~0u, (int)(ld_relaxed(p) - target) >= 0) & mask) { if (++n > SPIN_LIMIT) __trap(); }
    asm volatile("fence.acquire.gpu;" ::: "memory");
}
__device__ __forceinline__ float silu_bf(uint32_t cbits) {
    const float c = __uint_as_float(cbits << 16);
    return bf_round(__fdividef(c, 1.f + fminf(ex2(-1.4426950408889634f * c), 1e30f)));
}
__device__ __forceinline__ void gemv_part(uint32_t wmbuf, int npanel, int wp, int lane) {
    const uint32_t wa = wmbuf + wp * 512 + (8 * (lane >> 4) + (lane & 7)) * 32 + ((lane >> 3) & 1) * 16;
    uint2 B[4];
#pragma unroll
    for (int i = 0; i < 4; i++) { const float2 v = lds2f(wmbuf + 28672 + (wp + 8 * i) * 32 + (lane & 3) * 8); B[i] = make_uint2(__float_as_uint(v.x), __float_as_uint(v.y)); }
#pragma unroll 1
    for (int pn = 0; pn < npanel; pn++) {
        float d[4] = {};
        uint32_t A[16];
#pragma unroll
        for (int i = 0; i < 4; i++) ldsm4t(wa + pn * 14336 + (i < 3 || wp < 4 ? i : 0) * 4096, A + 4 * i);
#pragma unroll
        for (int i = 0; i < 4; i++) mma16816(d, A[4 * i], A[4 * i + 1], A[4 * i + 2], A[4 * i + 3], B[i].x, B[i].y);
        if ((lane & 3) == 0) {
            sts1(wmbuf + 29696 + (wp * 32 + pn * 16 + (lane >> 2)) * 4, __float_as_uint(d[0]));
            sts1(wmbuf + 29696 + (wp * 32 + pn * 16 + 8 + (lane >> 2)) * 4, __float_as_uint(d[2]));
        }
    }
}
__device__ __forceinline__ const uint4* mod_src(int i, int r, int j, bool p2) {
    i = min(i, p2 ? 251 : 223);
    return (const uint4*)g_mod + (r & 7) * (6 * DM / 4) + (i < 224 ? (p2 ? 336 : 0) + i : (i < 238 ? 14 * j + i : 14 * j + i + 322));
}
__device__ __forceinline__ void mod_store(uint32_t sb, uint4 v, const uint4* src, int i, uint32_t sc) {
    const uint32_t tag = lds1(sb + M_EPOCH) + 1;
    while (__any_sync(~0u, (((v.x ^ tag) | (v.y ^ tag) | (v.z ^ tag) | (v.w ^ tag)) & 0xFFFFu) != 0u) && !sc) v = ld_relaxed4(src);
    if (i < 224) {
        const int isc = i >= 112, c4 = i - 112 * isc;
        const uint32_t a = sb + M_ST + (c4 >> 2) * 64 + (c4 & 1) * 32 + (c4 & 2) * 4 + (isc ? 0 : 4);
        sts1(a, __byte_perm(v.x, v.y, 0x7632));
        sts1(a + 16, __byte_perm(v.z, v.w, 0x7632));
    } else if (i < 252) {
        sts4(sb + M_G + (i - 224) * 16, make_uint4(v.x & 0xFFFF0000u, v.y & 0xFFFF0000u, v.z & 0xFFFF0000u, v.w & 0xFFFF0000u));
    }
}
__device__ __forceinline__ int pass_f(int fs, int ps) { return 224 * fs + ((fs & 1) ? (ps == 0 ? 96 : ps == 1 ? 32 : 0) : (ps == 0 ? 0 : ps == 1 ? 128 : 192)); }
__device__ __forceinline__ constexpr uint32_t slot_off(int l) { return l * 16384; }
__device__ __forceinline__ constexpr int g1_slot(int s) { return s < 3 ? s : s < 6 ? s + 1 : s == 6 ? 3 : s % 7; }
__device__ __noinline__ void x1_fix(const uint32_t* g, uint32_t sa, int s) {
#pragma unroll 1
    for (int k = 4 * s; k < 4 * s + 4;) {
        const uint4 v = ld_relaxed4((const uint4*)(g + k * 256));
        sts4(sa + k * 1024, v);
        k += 2 * __all_sync(~0u, min(min(v.x, v.y), min(v.z, v.w)) != 0u);
    }
    __syncwarp();
}
__device__ __forceinline__ void ln_coeffs(float mean, float msq, uint32_t& r2, uint32_t& n2) {
    const float rs = bf_round(rsqrtf(fmaxf(msq - mean * mean, 0.f) + 1e-5f));
    r2 = pack2(rs, rs);
    n2 = pack2(-mean * rs, -mean * rs);
}

#define LOADW bulk_e(dst, g_wd + (size_t)((f >> 5) * 4 + nq) * 1792, 7168, bar);
template <int sec> __device__ __forceinline__ void ring_loader(const Params& p, uint32_t sb_, int r_, int j_, int lane) {
    const uint32_t sb = opaque(sb_);
    const int r = opaque(r_), j = opaque(j_), nq = j >> 1, fs = 4 * (j & 1) + nq;
    const int fa = pass_f(fs, 0), fb = pass_f(fs, 1), fc = pass_f(fs, 2);
    const uint32_t* h2src = (const uint32_t*)__shfl_sync(~0u, (unsigned long long)(p.actb + (size_t)r * RB_WORDS + RB_H2), 0);
    const CUtensorMap* gmap = (const CUtensorMap*)__shfl_sync(~0u, (unsigned long long)(&p.ga + sec), 0);
#define BAR(i) (sb + M_BAR + 8 * (i))
#define kh (j & 1)
            int sl = 0;
            mbar_wait(BAR(B_PUB + 2), 0);
            wait_flags(g_flag + (8 * r + j) * 128 + 96 + lane, lds1(sb + M_EPOCH) + 1, 0xFFFFu);
            fence_async_global();
#pragma unroll 1
            for (int s = 0; s < 28; s++) {
                const int ps = s < 14 ? 0 : s < 21 ? 1 : 2;
                const uint32_t half = ps < 2 ? 8192 : 4096;
                const int sp = s >= 3 && s < 7 ? (s == 6 ? 3 : s + 1) : sl;
                mbar_wait(BAR(B_EMPTY + sp), (s >= 7 && s < 14) || s >= 21);
                expect_e(BAR(B_FULL + sp), half);
                tma3_e(sb + slot_off(sp) + sec * half, gmap + 2 * ps, 0, ps ? 64 * sl : 32 * s, ps == 0 ? fa >> 6 : ps == 1 ? fb >> 6 : fc >> 5, BAR(B_FULL + sp));
                sl = sl == 6 ? 0 : sl + 1;
            }
            if (!sec) PROFH(3);
#pragma unroll 1
            for (int e = 0; e < 4; e++) {
                const uint32_t dst = sb + slot_off(e) + sec * 8192, bar = BAR(B_FULL + e);
                const int f = (e < 2 ? fa + 64 * e : e == 2 ? fb : fc) + 32 * sec;
                mbar_wait(BAR(B_EMPTY + e), 0);
                expect_e(bar, e == 3 && sec ? 0 : 7168);
                if (!(e == 3 && sec)) { LOADW }
            }
            sl = 4;
            int e = 4;
#pragma unroll 1
            for (int grp = 0; grp < 9; grp++) {
                const int ps = grp >= 6 ? 2 : grp >= 3 ? 1 : 0;
                int sidx = grp - 3 * ps;
                if (sec && sidx == 0) { mbar_wait(BAR(B_HRDY + ps), 0); fence_async_global(); }
                sidx += sidx >= nq;
                int f = pass_f(4 * kh + sidx, ps);
#pragma unroll 1
                for (int k = 4 >> ps; k > 0; k--, e++, f += 32) {
                    const uint32_t dst = sb + slot_off(sl), bar = BAR(B_FULL + sl);
                    mbar_wait(BAR(B_EMPTY + sl), e >= 12 && e < 24);
                    if (e < WIN_END && e >= WIN) mbar_wait(BAR(B_FULL + (sl >= WIN ? sl - WIN : sl + 12 - WIN)), e - WIN >= 12);
                    expect_e(bar, sec ? 8192 : 7168);
                    if (!sec) { LOADW }
                    else bulk_e(dst + 8192, h2src + f * 64, 8192, bar);
                    sl = sl == 11 ? 0 : sl + 1;
                }
            }
            if (!sec) PROFH(4);
}

#define act (p.actb + (size_t)r * RB_WORDS)
#define PROF_PARAMS
#define PROF_ARGS
__device__ __noinline__ void helper_late(const Params& p, int r_, int j_, int warp_ PROF_PARAMS) {
    extern __shared__ __align__(1024) unsigned char smem[];
    const uint32_t sb = (uint32_t)__cvta_generic_to_shared(smem);
    const int r = opaque(r_), j = opaque(j_), warp = opaque(warp_), nq = j >> 1, b = 8 * r + j;
    {
        const int lane = fresh_tid() & 31;
        const uint32_t target = lds1(sb + M_EPOCH) + 1;
        if (warp == 8) { expect_e(BAR(B_XCH), 14336); expect_e(BAR(B_XCH + 1), 14336); }
            if (warp == 9) {
#pragma unroll 1
                for (int kv = 0; kv < 2; kv++) {
                    mbar_wait(BAR(B_PUB + kv), 0);
                    wait_flags(g_flag + b * 128 + lane, target, (r >= 2 ? 6u : r == 1 ? 2u : 0u) << (8 * kv));
                    fence_async_global();
                    const uint32_t dst = sb + OFF_Y + (kv ? Y_VR : Y_K);
                    expect_e(BAR(B_KRFULL + kv), r >= 2 ? 28672 : r == 1 ? 14336 : 0);
                    if (r >= 2) bulk_e(dst, act - 2 * RB_WORDS + RB_KV + j * 7168 + kv * 3584, 14336, BAR(B_KRFULL + kv));
                    if (r >= 1) bulk_e(dst + 14336, act - RB_WORDS + RB_KV + j * 7168 + kv * 3584, 14336, BAR(B_KRFULL + kv));
                }
            } else if (warp == 11) {
                mbar_wait(BAR(B_VRFULL), 0);
                l2_prefetch_e((const char*)p.wg + (size_t)b * 12544, 12544);
                l2_prefetch_e((const char*)p.wu + (size_t)b * 12544, 12544);
#pragma unroll 1
                for (int k = 0; k < (r < 12 ? 2 : 1); k++) {
                    const int u = 28 * kh + r + 16 * k;
                    expect_e(BAR(B_XFULL + k), 7168);
                    tma3_e(sb + OFF_Y + 102400, &p.dn, 0, 32 * u, 7 * j, BAR(B_XFULL + k));
                    tma3_e(sb + OFF_Y + 102400 + 3584, &p.dn, 0, 32 * u, 7 * (j ^ 1), BAR(B_XFULL + k));
                    mbar_wait(BAR(B_XFULL + k), 1);
                    asm volatile("{\n.reg .pred p;\nelect.sync _|p, 0xffffffff;\n@p cp.async.bulk.global.shared::cta.bulk_group [%0], [%1], 7168;\n"
                                 "cp.async.bulk.commit_group;\ncp.async.bulk.wait_group 0;\n}" ::"l"(g_wd + (size_t)(u * 4 + nq) * 1792), "r"(sb + OFF_Y + 102400) : "memory");
                    __syncwarp();
                }
                warp_arrive(BAR(B_WMFREE));
                fence_gpu();
                if (lane < 16) st_relaxed(g_flag + (8 * lane + j) * 128 + 96 + r, target);
            }
        if (warp == 8 || warp == 11) {
            const int sec = warp == 11;
            if (sec) ring_loader<1>(p, sb, r, j, lane); else ring_loader<0>(p, sb, r, j, lane);
            mbar_wait(BAR(B_DONE), 0);
        } else if (warp == 9) {
#pragma unroll
            for (int ev = 0; ev < 4; ev++) { expect_e(BAR(B_GFULL + ev), ev < 2 ? HALF / 2 : 16384 + 4096); expect_e(BAR(B_XFULL + 2 + ev), ev < 2 ? HALF / 2 : HALF - 16384); }
            mbar_wait(BAR(B_PUB + 2), 0);
            const uint32_t* fp = g_flag + b * 128 + 32 + lane;
            const int par = (target - 1) & 1;
#pragma unroll 1
            for (int n = 0, ev = 0; ev < 4; n++) {
                if (ev == 1) { mbar_wait(BAR(B_WMFREE), 1); mbar_wait(BAR(B_PUB + 3), 0); }
                uint32_t ok = __ballot_sync(~0u, (int)(ld_relaxed(fp) - target) >= 0) >> (8 * ev);
                while ((ok & 0xFFu) == 0xFFu) {
                    asm volatile("fence.acquire.gpu;" ::: "memory");
                    fence_async_global();
                    const int tile = (ev & 1) + (ev >> 1) * par * 2;
                    const uint32_t dst = sb + (ev == 0 ? OFF_X : OFF_Y + (ev & 1) * HALF), first = ev < 2 ? HALF / 2 : 16384;
                    const char* src = (const char*)(act + RB_O + ((ev >> 1) * 2 + tile) * 14336);
                    if (ev >= 2) bulk_e(sb + OFF_X + X_STAT + (ev & 1) * 4096, act + RB_ST + tile * 1024, 4096, BAR(B_GFULL + ev));
                    bulk_e(dst, src, first, BAR(B_GFULL + ev));
                    bulk_e(dst + first, src + first, HALF - first, BAR(B_XFULL + 2 + ev));
                    if (ev) PROFH(4 + ev);
                    ev++; ok >>= 8;
                }
                if (n > SPIN_LIMIT) __trap();
            }
            mbar_wait(BAR(B_XFULL + 5), 1);
#pragma unroll 1
            for (int hf = 0; hf < 2; hf++) {
                const int tile = (par ^ 1) * 2 + hf;
                uint4* xz = (uint4*)(act + RB_X1 + tile * 14336 + j * 1792) + lane;
#pragma unroll
                for (int i = 0; i < 14; i++) xz[i * 32] = make_uint4(0, 0, 0, 0);
                ((uint4*)(act + RB_ST + (tile * 8 + j) * 128))[lane] = make_uint4(0, 0, 0, 0);
            }
#pragma unroll 1
            for (int ps = 0; ps < 3; ps++) {
                mbar_wait(BAR(B_PUB + 6 + ps), 0);
                wait_flags(g_flag + b * 128 + 64 + lane, target, (0x55u << kh) << (8 * ps));
                warp_arrive(BAR(B_HRDY + ps));
                PROFH(9 + ps);
            }
        } else {
#pragma unroll 1
            for (int k = 0; k < 9; k++) {
                uint32_t* fp = k < 2 ? g_flag + (b + 8 * lane) * 128 + k * 8 + lane : g_flag + (8 * r + lane) * 128 + 16 + k * 8 + j;
                mbar_wait(BAR(B_PUB + k), 0);
                if (k != 4 && k != 5) fence_gpu();
                if (k < 2 ? (lane == 1 || lane == 2) : lane < 8) st_relaxed(fp, target);
                if (k >= 3 && k <= 5) PROFH(k - 3);
            }
        }
    }
}

__global__ void __cluster_dims__(2, 1, 1) __launch_bounds__(384, 1) fused_block_kernel(const __grid_constant__ Params p) {
    extern __shared__ __align__(1024) unsigned char smem[];
    const uint32_t sb = (uint32_t)__cvta_generic_to_shared(smem);
    const int tid = threadIdx.x, lane = tid & 31, warp = __shfl_sync(~0u, tid >> 5, 0);
    const int m = blockIdx.x >> 1;
    int r, nq;
    {
        int g, i;
        if (m < MAP_S) { g = m < 4 ? 15 : 16; i = m & 3; }
        else if (m < MAP_S + 32) { g = (m - MAP_S) & 7; i = (m - MAP_S) >> 3; }
        else if (m < MAP_S + 60) { i = (m - MAP_S - 32) / 7; g = 8 + (m - MAP_S - 32) - 7 * i; }
        else { g = 16; i = m & 3; }
        r = g; nq = i;
    }
    const int j = opaque(2 * nq + (blockIdx.x & 1)), b = 8 * r + j, fs = 4 * kh + nq;
    const uint32_t sc = r == 16;
    if (lane == 0 && warp < 9 && warp != 6 && warp != 7) {
        const int i0 = warp == 8 ? 0 : 8 + 8 * warp, cnt = warp == 0 || warp == 8 ? 1 : warp < 3 ? 2 : 8;
#pragma unroll
        for (int k = 0; k < 8; k++) if (i0 + k != B_WMFULL) mbar_init(BAR(i0 + k), cnt);
        asm volatile("fence.mbarrier_init.release.cluster;" ::: "memory");
        fence_async_smem();
    }

    if (warp >= 8) {
        const int lane = fresh_tid() & 31;
        const bool early = kh == 0, gemv = r < 14;
        const int mcol = early ? 16 * (4 * r + nq) : 2 * DM + 32 * (4 * r + nq);
        const uint32_t wmbuf = sb + OFF_Y + HALF;
        asm volatile("setmaxnreg.dec.sync.aligned.u32 56;");
        if (warp == 9) {
#pragma unroll
            for (int i = 56; i < 64; i++) init_e(BAR(i), 1);
            fence_async_smem();
        }
        if (warp == 8) { init_e(BAR(B_WMFULL), 1); fence_async_smem(); }
        bar_arrive(0, 384);
        asm volatile("barrier.cluster.arrive.relaxed.aligned;" ::: "memory");
        if (warp == 8) {
            if (!sc) {
                expect_e(BAR(B_WMFULL), gemv ? 28672 >> early : 0);
                if (early && gemv) { tma3_e(wmbuf, &p.wm, mcol, 0, 0, BAR(B_WMFULL)); tma3_e(wmbuf + 7168, &p.wm, mcol, 224, 0, BAR(B_WMFULL)); }
#pragma unroll 1
                for (int kb = 0; kb < 7; kb++) {
                    expect_e(BAR(B_XFULL + kb), 16384);
                    tma3_e(sb + OFF_X + kb * 16384, &p.xm, 64 * kb, 128 * r, 0, BAR(B_XFULL + kb));
                }
            }
#pragma unroll 1
            for (int mt = 0; mt < 4; mt++) {
                if (mt == 1) {
                    if (!early && gemv) {
#pragma unroll 1
                        for (int k = 0; k < 4; k++) tma3_e(wmbuf + k * 7168, &p.wm, mcol + (k >> 1) * 16, (k & 1) * 224, 0, BAR(B_WMFULL));
                    }
                    bar_sync(9, 384);
                    if (sc) return;
                    mbar_wait(BAR(B_WMFREE), 0);
                }
                if (mt) mbar_wait(BAR(mt == 1 ? B_MOD1 : mt == 2 ? B_XFREE : B_VRFULL), 0);
                const uint32_t bar = BAR(mt == 3 ? B_WOFULL : B_FULLK + mt), dst = sb + (mt < 2 ? OFF_Y : OFF_X) + (mt & 1) * HALF;
                const int c0 = (mt < 2 ? DM + DM * mt : 0) + 56 * j - 8 * kh;
                if (!sc) {
                    expect_e(bar, HALF);
                    tma3_e(dst, mt == 3 ? &p.wo : &p.qkv, c0, 0, 0, bar);
                    tma3_e(dst + HALF / 2, mt == 3 ? &p.wo : &p.qkv, c0, 224, 0, bar);
                }
            }
        } else {
            if (warp == 10 && !sc) l2_prefetch_e((const char*)p.wqkv + (size_t)b * 9408, 9408);
            bar_sync(9, 384);
            if (sc) return;
            if (warp == 11) {
                const int col = mcol + (early ? lane & 15 : lane);
                const uint32_t tag = (lds1(sb + M_EPOCH) + 1) & 0xFFFFu;
                mbar_wait(BAR(B_GEMV), 0);
                float sum = 0.f;
#pragma unroll
                for (int i = 0; i < 8; i++) sum += *(const float*)(smem + OFF_Y + HALF + 29696 + (i * 32 + col - mcol) * 4);
                sum = bf_round(sum);
                if ((col >= DM && col < 2 * DM) || (col >= 4 * DM && col < 5 * DM)) sum += 1.f;
                uint32_t* mg = g_mod + col + (early ? (lane >> 4) * 4 * 6 * DM : 0);
#pragma unroll 1
                for (int i = gemv ? (early ? 4 : 8) : 0; i > 0; i--, mg += 6 * DM) st_relaxed(mg, (pack2(sum, 0.f) << 16) | tag);
                warp_arrive(BAR(B_WMFREE));
            }
        }
    }
    if (LIKELY(warp < 8)) {
        const int w = warp >> 2, wi = warp & 3;
#define COORDS const int t = fresh_tid() & 127, lane = t & 31, q = lane & 3, lr = lane >> 2, ra = 64 * w + 16 * wi + lr; \
        const uint32_t lx = (lane >> 4) ^ (lane & 7), mrow = (64 * w + 16 * wi + ((lane >> 3) & 1) * 8 + (lane & 7)) * 128; \
        (void)q; (void)lr; (void)ra; (void)lx; (void)mrow;
        const int sid = 2 * (j & 3) + w;
#define RUN(k) (!sc || sid == (k))
#define WAIT(i, par) mbar_wait_c(BAR(i), (par) | sc)
        constexpr uint64_t DB128 = dconst(4096, 1024, 1);
        {
            const int wd = fresh_tid();
            const uint32_t cb = wd < 224 ? __ldg((const uint32_t*)p.c + wd) : 0u;
            if (wd == 255 && !sc) sts1(sb + M_EPOCH, atomicAdd(&g_ticket, 1u) / NCTA);
            sts1(sb + OFF_Y + HALF + 28672 + (wd >> 3) * 32 + (wd & 3) * 8 + (wd & 4), pack2(silu_bf(cb & 0xFFFFu), silu_bf(cb >> 16)));
        }
        bar_arrive(9, 384);
        bar_sync(0, 384);
        asm volatile("barrier.cluster.arrive.relaxed.aligned;" ::: "memory");
        asm volatile("setmaxnreg.inc.sync.aligned.u32 224;");
        PROFC(0);
        uint32_t xr[16];
        {
            COORDS
            uint32_t h[112];
            if (RUN(0)) {
                float ds[4] = {}, da[2][4] = {}, db[2][4] = {};
                const uint32_t ONE2 = 0x3F803F80u;
                if (kh == 0) { WAIT(B_WMFULL, 0); gemv_part(sb + OFF_Y + HALF, 1, warp, lane); warp_arrive(BAR(B_GEMV)); }
#pragma unroll
                for (int kb = 0; kb < 7; kb++) {
                    WAIT(B_XFULL + kb, 0);
#pragma unroll
                    for (int k4 = 0; k4 < 4; k4++) ldsm4(sb + OFF_X + mrow + kb * 16384 + (((2 * k4) ^ lx) << 4), h + 16 * kb + 4 * k4);
#pragma unroll
                    for (int k4 = 0; k4 < 4; k4++) {
                        const uint32_t* f = h + 16 * kb + 4 * k4;
                        mma16816(ds, f[0], f[1], f[2], f[3], ONE2, ONE2);
                        mma1688(da[0], f[0], f[1], f[0]); mma1688(db[0], f[0], f[1], f[1]);
                        mma1688(da[1], f[2], f[3], f[2]); mma1688(db[1], f[2], f[3], f[3]);
                    }
                }
#pragma unroll
                for (int i = 0; i < 4; i++) {
                    const int ch = 7 * j + 2 * i + (lane >> 4);
                    ldsm4(sb + OFF_X + mrow + (ch >> 3) * 16384 + (((ch ^ lane) & 7) << 4), xr + 4 * i);
                }
                warp_arrive(BAR(B_XFREE));
                float qa = (lr & 1) ? da[0][1] + da[1][1] : da[0][0] + da[1][0];
                float qb = (lr & 1) ? db[0][3] + db[1][3] : db[0][2] + db[1][2];
                const int src = (lane & ~3) | (lr >> 1);
                qa = __shfl_sync(~0u, qa, src);
                qb = __shfl_sync(~0u, qb, src);
                uint32_t ra2, na2, rb2, nb2;
                ln_coeffs(ds[0] * (1.f / DM), qa * (1.f / DM), ra2, na2);
                ln_coeffs(ds[2] * (1.f / DM), qb * (1.f / DM), rb2, nb2);
#pragma unroll
                for (int i = 0; i < 112; i += 2) { h[i] = hfma2(h[i], ra2, na2); h[i + 1] = hfma2(h[i + 1], rb2, nb2); }
                if (kh == 1) { WAIT(B_WMFULL, 0); gemv_part(sb + OFF_Y + HALF, 2, warp, lane); warp_arrive(BAR(B_GEMV)); }
            } else { reg_def<112>(h); reg_def<16>(xr); }
            PROFC(1);
            if (RUN(1)) {
                float ak[28], av[28], aq[28];
                uint32_t kp[14], vp[14];
                const uint64_t bq0 = (DB128 & ~0xFFFFFFFFull) | (mkdesc(sb + OFF_X, DB128) + kh), bk0 = bq0 + (OFF_Y >> 4), bv0 = bk0 + (HALF >> 4);
                uint32_t* kvg = act + RB_KV + j * 7168 + (8 * w + 2 * wi) * 224 + lane;
                {
                    const int i = min(fresh_tid(), 223);
                    const uint4* src = mod_src(i, r, j, false);
                    mod_store(sb, ld_relaxed4(src), src, i, sc);
                    if (!sc) bar_sync(3, 256);
                    if (warp == 0) warp_arrive(BAR(B_MOD1));
                }
                WAIT(B_FULLK, 0);
                PROFC(2);
                reg_def<28>(ak);
#pragma unroll
                for (int g4 = 0; g4 < 4; g4++) {
#pragma unroll
                    for (int ks = 7 * g4; ks < 7 * g4 + 7; ks++) {
                        const uint4 st = *(const uint4*)(smem + M_ST + ks * 64 + q * 16);
                        h[4 * ks] = hfma2(h[4 * ks], st.x, st.y); h[4 * ks + 1] = hfma2(h[4 * ks + 1], st.x, st.y);
                        h[4 * ks + 2] = hfma2(h[4 * ks + 2], st.z, st.w); h[4 * ks + 3] = hfma2(h[4 * ks + 3], st.z, st.w);
                    }
                    WG_FENCE();
#pragma unroll
                    for (int ks = 7 * g4; ks < 7 * g4 + 7; ks++) wgmma_rl_56(ak, h[4 * ks], h[4 * ks + 1], h[4 * ks + 2], h[4 * ks + 3], bk0 + ks * 128, ks != 0);
                }
                WG_COMMIT();
                PROFC(3);
                WAIT(B_FULLV, 0);
                reg_def<28>(av);
                WG_FENCE();
#pragma unroll
                for (int ks = 0; ks < 8; ks++) wgmma_rl_56(av, h[4 * ks], h[4 * ks + 1], h[4 * ks + 2], h[4 * ks + 3], bv0 + ks * 128, ks != 0);
                WG_COMMIT();
                WG_WAIT(1);
                reg_fence<28>(ak);
#pragma unroll
                for (int g = 0; g < 7; g++) {
                    kp[2 * g] = pack2(ak[4 * g], ak[4 * g + 1]); kp[2 * g + 1] = pack2(ak[4 * g + 2], ak[4 * g + 3]);
                    kvg[g * 32] = kp[2 * g]; kvg[224 + g * 32] = kp[2 * g + 1];
                }
                warp_arrive(BAR(B_PUB));
                PROFC(4);
                WG_FENCE();
#pragma unroll
                for (int ks = 8; ks < 28; ks++) wgmma_rl_56(av, h[4 * ks], h[4 * ks + 1], h[4 * ks + 2], h[4 * ks + 3], bv0 + ks * 128, 1);
                WG_COMMIT();
                WAIT(B_FULLQ, 0);
                reg_def<28>(aq);
                WG_FENCE();
#pragma unroll
                for (int ks = 0; ks < 8; ks++) wgmma_rl_56(aq, h[4 * ks], h[4 * ks + 1], h[4 * ks + 2], h[4 * ks + 3], bq0 + ks * 128, ks != 0);
                WG_COMMIT();
                WG_WAIT(1);
                reg_fence<28>(av);
#pragma unroll
                for (int g = 0; g < 7; g++) {
                    vp[2 * g] = pack2(av[4 * g], av[4 * g + 1]); vp[2 * g + 1] = pack2(av[4 * g + 2], av[4 * g + 3]);
                    kvg[3584 + g * 32] = vp[2 * g]; kvg[3584 + 224 + g * 32] = vp[2 * g + 1];
                }
                warp_arrive(BAR(B_PUB + 1));
                const uint4* msrc = mod_src(128 * w + t, r, j, true);
                const uint4 mv = ld_relaxed4(msrc);
                PROFC(5);
                WG_FENCE();
#pragma unroll
                for (int ks = 8; ks < 28; ks++) wgmma_rl_56(aq, h[4 * ks], h[4 * ks + 1], h[4 * ks + 2], h[4 * ks + 3], bq0 + ks * 128, 1);
                WG_COMMIT();
                WAIT(B_PUB + 1, 0);
                mod_store(sb, mv, msrc, 128 * w + t, sc);
                const uint32_t rg = 8 * w + 2 * wi + ((lane >> 3) & 1);
                const uint32_t ko = sb + OFF_Y + Y_KOWN + rg * 896 + (lane & 7) * 16, qo = sb + OFF_Y + Y_Q + rg * 1024 + (lane >> 4) * 128 + (lane & 7) * 16;
#pragma unroll
                for (int g = 0; g < 6; g += 2) {
                    stsm4(ko + (g + (lane >> 4)) * 128, kp[2 * g], kp[2 * g + 1], kp[2 * g + 2], kp[2 * g + 3]);
                    stsm4(ko + (Y_VOWN - Y_KOWN) + (g + (lane >> 4)) * 128, vp[2 * g], vp[2 * g + 1], vp[2 * g + 2], vp[2 * g + 3]);
                }
                stsm4(ko + (lane >> 4) * (Y_VOWN - Y_KOWN) + 6 * 128, kp[12], kp[13], vp[12], vp[13]);
                WG_WAIT(0);
                reg_fence<28>(aq);
                __syncwarp();
                if (lane < 3 && w == 1) mbar_arrive(BAR(B_EMPTY + lane));
                uint32_t qp[14];
#pragma unroll
                for (int i = 0; i < 14; i++) qp[i] = pack2(aq[2 * i], aq[2 * i + 1]);
                stsm4(qo, qp[0], qp[1], qp[2], qp[3]);
                stsm4(qo + 256, qp[4], qp[5], q < 2 ? qp[6] : 0u, q < 2 ? qp[7] : 0u);
                stsm4(qo + 512, q < 2 ? 0u : qp[6], q < 2 ? 0u : qp[7], qp[8], qp[9]);
                stsm4(qo + 768, qp[10], qp[11], qp[12], qp[13]);
                if (!sc) bar_sync(3, 256);
            }
        }
        PROFC(6);
        WAIT(B_KRFULL, 0);
        PROFC(7);
        if (RUN(2)) {
#pragma unroll 1
            for (int hf = sc; hf < 2; hf++) {
                COORDS
                float s[136];
                float na = 0.f, nb = 0.f;
                const float CS = 0.18898223650461361f * 1.4426950408889634f;
                const int kg0 = 8 * hf + 2 * wi;
                const int pmin = 16 - 8 * r - 4 * hf - wi;
                const float NEG = __int_as_float(0xFF800000);
                {
                    uint32_t F[8];
                    const uint32_t qa = sb + OFF_Y + Y_Q + (kg0 + ((lane >> 3) & 1)) * 1024 + (4 * w + (lane >> 4)) * 128 + (lane & 7) * 16;
                    ldsm4(qa, F); ldsm4(qa + 256, F + 4);
                    uint32_t ka = sb + OFF_Y + Y_K + kg0 * 896 + (3 * w + (lane >> 3)) * 128 + (lane & 7) * 16;
#pragma unroll
                    for (int g = 0; g < 34; g++) {
                        uint32_t B[4];
                        if (g >= 12 && g % 4 == 0) ka += __float_as_uint(s[4 * (g - 12)]) & p.zero;
                        ldsm4(ka + g * 896, B);
                        mma16816_first(s + 4 * g, F[0], F[1], F[2], F[3], B[0], B[1]);
                        mma16816_v(s + 4 * g, F[4], F[5], F[6], F[7], B[2], B[3]);
                    }
                    const bool c0 = 2 * q > lr, c1 = 2 * q + 1 > lr;
                    if (!c0) { s[0] = NEG; s[6] = NEG; }
                    if (!c1) { s[1] = NEG; s[7] = NEG; }
                    s[2] = NEG; s[3] = NEG;
                    if (c0) { s[128] = NEG; s[134] = NEG; }
                    if (c1) { s[129] = NEG; s[135] = NEG; }
                    s[132] = NEG; s[133] = NEG;
                    float ma = NEG, mb = NEG;
#pragma unroll
                    for (int pp = 0; pp < 17; pp++) {
                        const float* e = s + 8 * pp;
                        const float bias = pp < pmin ? NEG : 0.f;
                        ma = fmaxf(ma, fmaxf(fmaxf(e[0], e[1]), fmaxf(e[4], e[5])) + bias);
                        mb = fmaxf(mb, fmaxf(fmaxf(e[2], e[3]), fmaxf(e[6], e[7])) + bias);
                    }
                    ma = fmaxf(ma, __shfl_xor_sync(~0u, ma, 1)); mb = fmaxf(mb, __shfl_xor_sync(~0u, mb, 1));
                    ma = fmaxf(ma, __shfl_xor_sync(~0u, ma, 2)); mb = fmaxf(mb, __shfl_xor_sync(~0u, mb, 2));
                    na = -ma * CS; nb = -mb * CS;
                }
                PROFC(8 + 3 * hf);
                {
                    WAIT(B_VRFULL, 0);
                    float o[16] = {}, rs[4] = {};
                    uint32_t pk[2];
                    const uint32_t va = sb + OFF_Y + Y_VR + (kg0 + ((lane >> 3) & 1)) * 896 + (3 * w + (lane >> 4)) * 128 + (lane & 7) * 16;
#pragma unroll
                    for (int pp = 0; pp < 17; pp++) {
                        uint32_t B[8];
                        const uint32_t v = va + pp * 1792 + (pp == 16 || (pp >= 9 && kg0 + 2 * pp >= 32) ? Y_VOWN - 32 * 896 : 0);
                        ldsm4t(v, B); ldsm4t(v + 256, B + 4);
                        float e[8];
                        const float bias = __uint_as_float((pp < pmin ? 0xFF800000u : 0u) | ((pp < 2 ? B[0] : pk[pp & 1]) & p.zero));
#pragma unroll
                        for (int i = 0; i < 8; i++) e[i] = ex2(fmaf(s[8 * pp + i], CS, ((i & 2) ? nb : na) + bias));
                        const uint32_t p0 = pack2(e[0], e[1]), p1 = pack2(e[2], e[3]), p2 = pack2(e[4], e[5]), p3 = pack2(e[6], e[7]);
                        pk[pp & 1] = p3;
                        mma16816(rs, p0, p1, p2, p3, 0x3F803F80u, 0x3F803F80u);
#pragma unroll
                        for (int g = 0; g < 4; g++) mma16816(o + 4 * g, p0, p1, p2, p3, B[2 * g], B[2 * g + 1]);
                    }
                    PROFC(9 + 3 * hf);
                    const float ia = rcp(rs[0]), ib = rcp(rs[2]);
                    uint32_t* og = act + RB_O + hf * 14336 + (7 * j + 3 * w) * 256 + wi * 64 + lane;
#pragma unroll
                    for (int g = 0; g < 4; g++) {
                        if ((g == 3 - 3 * w) ? ((q >> 1) == w) : true) {
                            og[g * 256] = pack2(o[4 * g] * ia, o[4 * g + 1] * ia);
                            og[g * 256 + 32] = pack2(o[4 * g + 2] * ib, o[4 * g + 3] * ib);
                        }
                    }
                    warp_arrive(BAR(B_PUB + 2 + hf));
                    PROFC(10 + 3 * hf);
                }
            }
        }
        uint32_t x1p[14];
        COORDS
        constexpr uint64_t DT = dconst(1024, 128, 0);
        const int tile = opaque((lds1(sb + M_EPOCH) & 1) * 2 + w);
        if (RUN(4)) {
            float ac[28];
            const uint32_t ad = mkdesc(sb + (w ? OFF_Y + HALF : OFF_X), DT), bd = mkdesc(sb + OFF_X + HALF, DB128) + kh;
            WAIT(B_WOFULL, 0);
            WAIT(B_GFULL + w, 0);
            PROFC(28);
            reg_def<28>(ac);
#pragma unroll 1
            for (int u = 0; u < 4; u++) {
                if (u == 2) WAIT(B_XFULL + 2 + w, 1);
                WG_FENCE();
#pragma unroll
                for (int i = 0; i < 7; i++) wgmma_ss_56<DT, DB128>(ac, ad + (7 * u + i) * 128, bd + (7 * u + i) * 128, (u | i) != 0);
            }
            WG_COMMIT();
            WG_WAIT(0);
            reg_fence<28>(ac);
            PROFC(14);
            __syncwarp();
            if (lane < 3) mbar_arrive(BAR(B_EMPTY + 4 + lane));
            if (lane < 3 && w == 0) mbar_arrive(BAR(B_EMPTY + lane));
            float ds[4] = {}, da[4] = {}, db[4] = {};
            uint32_t* xo = act + RB_X1 + tile * 14336 + 7 * j * 256 + wi * 64 + lane;
#pragma unroll
            for (int g = 0; g < 7; g++) {
                const float2 ga = *(const float2*)(smem + M_G + (8 * g + 2 * q) * 4);
                x1p[2 * g] = pack2(fmaf(ga.x, ac[4 * g], bf_lo(xr[2 * g])), fmaf(ga.y, ac[4 * g + 1], bf_hi(xr[2 * g])));
                x1p[2 * g + 1] = pack2(fmaf(ga.x, ac[4 * g + 2], bf_lo(xr[2 * g + 1])), fmaf(ga.y, ac[4 * g + 3], bf_hi(xr[2 * g + 1])));
                st_relaxed(xo + g * 256, nz(x1p[2 * g])); st_relaxed(xo + g * 256 + 32, nz(x1p[2 * g + 1]));
                mma1688(ds, x1p[2 * g], x1p[2 * g + 1], 0x3F803F80u);
                mma1688(da, x1p[2 * g], x1p[2 * g + 1], x1p[2 * g]);
                mma1688(db, x1p[2 * g], x1p[2 * g + 1], x1p[2 * g + 1]);
            }
            const int src = (lane & ~3) | (lr >> 1);
            const float qa = __shfl_sync(~0u, (lr & 1) ? da[1] : da[0], src), qb = __shfl_sync(~0u, (lr & 1) ? db[3] : db[2], src);
            const float kk = (q & 1) ? ((q & 2) ? qb : qa) : ((q & 2) ? ds[2] : ds[0]);
            st_relaxed(act + RB_ST + ((tile * 8 + j) * 64 + 16 * wi + lr + 4 * (q & 2)) * 2 + (q & 1), nz(__float_as_uint(kk)));
            __syncwarp();
            if (lane < 2) mbar_arrive(BAR(B_PUB + 4 + w));
        } else reg_def<14>(x1p);
        PROFC(15);
        uint32_t h2a[32], h2b[24];
        {
            const int fa = pass_f(fs, 0), fb = pass_f(fs, 1), fc = pass_f(fs, 2);
            uint32_t* h2g = act + RB_H2 + (8 * w + 2 * wi) * 32 + lane;
            const uint32_t a0 = mkdesc(sb + OFF_Y + w * HALF, DT);
            if (RUN(3)) {
                uint32_t ra2, na2, rb2, nb2;
                {
                    const uint32_t* sg = act + RB_ST + ((tile * 8 + 2 * q) * 64 + 16 * wi + lr) * 2;
                    uint2 u[4];
                    WAIT(B_GFULL + 2 + w, 0);
                    PROFC(16);
#pragma unroll
                    for (int i = 0; i < 4; i++) { const float2 v = lds2f(sb + OFF_X + X_STAT + w * 4096 + ((2 * q + (i >> 1)) * 64 + 16 * wi + lr + 8 * (i & 1)) * 8); u[i] = make_uint2(__float_as_uint(v.x), __float_as_uint(v.y)); }
                    while (__any_sync(~0u, min(min(min(u[0].x, u[0].y), min(u[1].x, u[1].y)), min(min(u[2].x, u[2].y), min(u[3].x, u[3].y))) < 1u - sc)) {
#pragma unroll
                        for (int i = 0; i < 4; i++) u[i] = ld_relaxed2(sg + (i >> 1) * 128 + (i & 1) * 16);
                    }
                    warp_arrive(BAR(B_EMPTY + 3));
                    float v[4] = {__uint_as_float(u[0].x) + __uint_as_float(u[2].x), __uint_as_float(u[0].y) + __uint_as_float(u[2].y),
                                  __uint_as_float(u[1].x) + __uint_as_float(u[3].x), __uint_as_float(u[1].y) + __uint_as_float(u[3].y)};
#pragma unroll
                    for (int i = 0; i < 4; i++) { v[i] += __shfl_xor_sync(~0u, v[i], 1); v[i] += __shfl_xor_sync(~0u, v[i], 2); }
                    ln_coeffs(v[0] * (1.f / DM), v[1] * (1.f / DM), ra2, na2);
                    ln_coeffs(v[2] * (1.f / DM), v[3] * (1.f / DM), rb2, nb2);
                }
                const uint32_t ha = sb + OFF_Y + w * HALF + (lane >> 4) * 1024 + (2 * wi + ((lane >> 3) & 1)) * 128 + (lane & 7) * 16;
                const uint32_t sta = sb + M_ST + q * 16;
                const uint32_t* xg = act + RB_X1 + tile * 14336 + (lane >> 4) * 256 + wi * 64 + (lane & 15) * 4;
                uint32_t x[8];
                const uint32_t xs = sb + OFF_Y + w * HALF + (lane >> 4) * 1024 + wi * 256 + (lane & 15) * 16;
                uint4 st[2];
                auto load = [&](int s) {
                    if (s == 4) mbar_wait_c(BAR(B_XFULL + 4 + w), 1);
                    ldsm4(ha + s * 4096, x); ldsm4(ha + s * 4096 + 2048, x + 4);
                    st[0] = lds4(sta + s * 128); st[1] = lds4(sta + s * 128 + 64);
                };
                auto prep = [&](int s, uint32_t* f) {
                    if (__any_sync(~0u, min(min(min(x[0], x[1]), min(x[2], x[3])), min(min(x[4], x[5]), min(x[6], x[7]))) < 1u - sc)) {
                        WG_WAIT(0);
                        x1_fix(xg, xs, s);
                        ldsm4(ha + s * 4096, x); ldsm4(ha + s * 4096 + 2048, x + 4);
                    }
#pragma unroll
                    for (int i = 0; i < 2; i++) {
                        f[4 * i] = hfma2(hfma2(x[4 * i], ra2, na2), st[i].x, st[i].y); f[4 * i + 1] = hfma2(hfma2(x[4 * i + 1], rb2, nb2), st[i].x, st[i].y);
                        f[4 * i + 2] = hfma2(hfma2(x[4 * i + 2], ra2, na2), st[i].z, st[i].w); f[4 * i + 3] = hfma2(hfma2(x[4 * i + 3], rb2, nb2), st[i].z, st[i].w);
                    }
                    if (s < 13) load(s + 1);
                    stsm4(ha + s * 4096, f[0], f[1], f[2], f[3]); stsm4(ha + s * 4096 + 2048, f[4], f[5], f[6], f[7]);
                };
                float ac[128];
                uint32_t fr[3][8];
                const uint32_t bx = mkdesc(sb, DB128);
                reg_def<128>(ac);
                load(0);
                prep(0, fr[0]);
                PROFC(17);
#pragma unroll
                for (int s = 0; s < 14; s++) {
                    const uint32_t* f = fr[s % 3];
                    const uint32_t bd = bx + g1_slot(s) * 1024;
                    WAIT(B_FULL + g1_slot(s), s >= 7);
                    WG_FENCE();
                    wgmma_rs_256<DB128>(ac, f[0], f[1], f[2], f[3], bd, s != 0);
                    wgmma_rs_256<DB128>(ac, f[4], f[5], f[6], f[7], bd + 128, 1);
                    WG_COMMIT();
                    if (s < 13) prep(s + 1, fr[(s + 1) % 3]);
                    if (s > 0) { WG_WAIT(1); warp_arrive(BAR(B_EMPTY + g1_slot(s - 1))); }
                }
                fence_async_smem();
                PROFC(18);
                WG_WAIT(0);
                reg_fence<128>(ac);
                warp_arrive(BAR(B_EMPTY + 6));
#pragma unroll
                for (int g = 0; g < 16; g++) {
                    h2a[2 * g] = hmul2(pack2_relu(ac[4 * g], ac[4 * g + 1]), pack2(ac[64 + 4 * g], ac[64 + 4 * g + 1]));
                    h2a[2 * g + 1] = hmul2(pack2_relu(ac[4 * g + 2], ac[4 * g + 3]), pack2(ac[64 + 4 * g + 2], ac[64 + 4 * g + 3]));
                }
                bar_sync(1 + w, 128);
            } else reg_def<32>(h2a);
            PROFC(19);
            if (RUN(5)) {
                float ac[64];
                reg_def<64>(ac);
                const uint32_t bx = mkdesc(sb, dconst(8192, 1024, 1));
#pragma unroll kB
                for (int s = 0; s < 7; s++) {
                    WAIT(B_FULL + s, 0);
                    const uint32_t ad = a0 + s * 512, bd = bx + (slot_off(s) >> 4);
                    WG_FENCE();
#pragma unroll
                    for (int k = 0; k < 4; k++) wgmma_ss_128<DT, DB128>(ac, ad + k * 128, bd + k * 128, (s | k) != 0);
                    WG_COMMIT();
                    if (s == 1) {
#pragma unroll
                        for (int g = 0; g < 16; g++) { h2g[(fa / 8 + g) * 512] = h2a[2 * g]; h2g[(fa / 8 + g) * 512 + 32] = h2a[2 * g + 1]; }
                        warp_arrive(BAR(B_PUB + 6));
                    }
                    if (s > 0) { WG_WAIT(1); warp_arrive(BAR(B_EMPTY + s - 1)); }
                }
                WG_WAIT(0);
                reg_fence<64>(ac);
                warp_arrive(BAR(B_EMPTY + 6));
#pragma unroll
                for (int g = 0; g < 8; g++) {
                    h2b[2 * g] = hmul2(pack2_relu(ac[4 * g], ac[4 * g + 1]), pack2(ac[32 + 4 * g], ac[32 + 4 * g + 1]));
                    h2b[2 * g + 1] = hmul2(pack2_relu(ac[4 * g + 2], ac[4 * g + 3]), pack2(ac[32 + 4 * g + 2], ac[32 + 4 * g + 3]));
                }
            } else reg_def<16>(h2b);
            PROFC(27);
            if (RUN(6)) {
                float ac[32];
                reg_def<32>(ac);
                const uint32_t bx = mkdesc(sb, dconst(4096, 512, 2));
#pragma unroll kC
                for (int s = 0; s < 7; s++) {
                    WAIT(B_FULL + s, 1);
                    const uint32_t ad = a0 + s * 512, bd = bx + (slot_off(s) >> 4);
                    WG_FENCE();
#pragma unroll
                    for (int k = 0; k < 4; k++) wgmma_ss_64<DT, dconst(4096, 512, 2)>(ac, ad + k * 128, bd + k * 64, (s | k) != 0);
                    WG_COMMIT();
                    if (s == 1) {
#pragma unroll
                        for (int g = 0; g < 8; g++) { h2g[(fb / 8 + g) * 512] = h2b[2 * g]; h2g[(fb / 8 + g) * 512 + 32] = h2b[2 * g + 1]; }
                        warp_arrive(BAR(B_PUB + 7));
                    }
                    if (s > 0) { WG_WAIT(1); warp_arrive(BAR(B_EMPTY + s - 1)); }
                }
                WG_WAIT(0);
                reg_fence<32>(ac);
                __syncwarp();
                if (lane < 6) mbar_arrive(BAR(B_EMPTY + 6 + lane));
                PROFC(20);
#pragma unroll
                for (int g = 0; g < 4; g++) {
                    h2b[16 + 2 * g] = hmul2(pack2_relu(ac[4 * g], ac[4 * g + 1]), pack2(ac[16 + 4 * g], ac[16 + 4 * g + 1]));
                    h2b[16 + 2 * g + 1] = hmul2(pack2_relu(ac[4 * g + 2], ac[4 * g + 3]), pack2(ac[16 + 4 * g + 2], ac[16 + 4 * g + 3]));
                    h2g[(fc / 8 + g) * 512] = h2b[16 + 2 * g]; h2g[(fc / 8 + g) * 512 + 32] = h2b[16 + 2 * g + 1];
                }
                warp_arrive(BAR(B_PUB + 8));
                asm volatile("barrier.cluster.wait.aligned;" ::: "memory");
                if (lane == 0 && !sc) {
                    uint32_t rb;
                    asm volatile("mapa.shared::cluster.u32 %0, %1, %2;" : "=r"(rb) : "r"(BAR(B_PEER)), "r"(kh ^ 1));
                    asm volatile("mbarrier.arrive.relaxed.cluster.shared::cluster.b64 _, [%0];" ::"r"(rb) : "memory");
                }
            } else reg_def<8>(h2b + 16);
        }
        PROFC(21);
        if (RUN(7)) {
            float ac[56];
            reg_def<56>(ac);
            constexpr uint64_t DAN = dconst(2048, 128, 0);
            constexpr uint64_t DW = dconst(128, 512, 0);
            const uint32_t bx = mkdesc(sb, DW);
#pragma unroll
            for (int e = 0; e < 4; e++) {
                WAIT(B_FULL + e, 0);
                const uint32_t bd = bx + (slot_off(e) >> 4);
                const uint32_t* hh = e < 2 ? h2a + 16 * e : h2b + 16 * (e - 2);
                WG_FENCE();
#pragma unroll
                for (int k = 0; k < (e < 3 ? 4 : 2); k++) wgmma_rs_112<DW>(ac, hh[4 * k], hh[4 * k + 1], hh[4 * k + 2], hh[4 * k + 3], bd + (k >> 1) * 512 + (k & 1) * 16, (e | k) != 0);
                WG_COMMIT();
                if (e > 0) { WG_WAIT(1); warp_arrive(BAR(B_EMPTY + e - 1)); }
            }
            PROFC(22);
            uint32_t ad = mkdesc(sb + 4 * 16384 + 8192 + w * 1024, DAN), bd = bx + 4 * 1024, fb_ = BAR(B_FULL + 4), eb_ = BAR(B_EMPTY + 3), par = sc;
#pragma unroll 1
            for (int e = 4; e < 25; e++) {
                mbar_wait_c(fb_, par);
                WG_FENCE();
                wgmma_ss_112<DAN, DW>(ac, ad, bd, 1);
                wgmma_ss_112<DAN, DW>(ac, ad + 256, bd + 16, 1);
                WG_COMMIT();
                WG_WAIT(1);
                warp_arrive(eb_);
                eb_ = fb_ + 8 * (B_EMPTY - B_FULL);
                ad += 1024; bd += 1024; fb_ += 8;
                if (e == 11 || e == 23) { ad -= 12 * 1024; bd -= 12 * 1024; fb_ -= 96; par = (par ^ 1) | sc; }
            }
            mbar_wait_cluster(BAR(B_PEER), sc);
            WG_WAIT(0);
            reg_fence<56>(ac);
            PROFC(24);
            uint32_t rdst, rbar;
            asm volatile("mapa.shared::cluster.u32 %0, %1, %2;" : "=r"(rdst) : "r"(sb + OFF_Y + (5 + w) * 16384 + t * 16), "r"(kh ^ 1 ^ sc));
            asm volatile("mapa.shared::cluster.u32 %0, %1, %2;" : "=r"(rbar) : "r"(BAR(B_XCH + w)), "r"(kh ^ 1 ^ sc));
#pragma unroll
            for (int g = 0; g < 7; g++) {
                const float v0 = ac[28 + 4 * g + 0], v1 = ac[28 + 4 * g + 1];
                const float v2 = ac[28 + 4 * g + 2], v3 = ac[28 + 4 * g + 3];
                if (!sc) asm volatile("st.async.shared::cluster.mbarrier::complete_tx::bytes.v4.f32 [%0], {%1,%2,%3,%4}, [%5];"
                             ::"r"(rdst + g * 2048), "f"(v0), "f"(v1), "f"(v2), "f"(v3), "r"(rbar) : "memory");
            }
            mbar_wait_cluster(BAR(B_XCH + w), sc);
            PROFC(25);
            bf16* og = (sc ? (bf16*)act : p.out + (size_t)128 * r * DM) + (size_t)ra * DM + 56 * j + 2 * q;
#pragma unroll
            for (int g = 0; g < 7; g++) {
                const uint4 rv = *(const uint4*)(smem + OFF_Y + (5 + w) * 16384 + t * 16 + g * 2048);
                const float2 gb = *(const float2*)(smem + M_G + 224 + (8 * g + 2 * q) * 4);
                const float v0 = ac[4 * g + 0] + __uint_as_float(rv.x), v1 = ac[4 * g + 1] + __uint_as_float(rv.y);
                const float v2 = ac[4 * g + 2] + __uint_as_float(rv.z), v3 = ac[4 * g + 3] + __uint_as_float(rv.w);
                *(uint32_t*)(og + 8 * g) = pack2(fmaf(gb.x, v0, bf_lo(x1p[2 * g])), fmaf(gb.y, v1, bf_hi(x1p[2 * g])));
                *(uint32_t*)(og + 8 * DM + 8 * g) = pack2(fmaf(gb.x, v2, bf_lo(x1p[2 * g + 1])), fmaf(gb.y, v3, bf_hi(x1p[2 * g + 1])));
            }
        }
        PROFC(26);
        bar_sync(1 + w, 128);
        if (wi == 0) warp_arrive(BAR(B_DONE));
        return;
    }
    helper_late(p, r, j, warp PROF_ARGS);
}

#undef act
typedef CUresult (*EncodeFn)(CUtensorMap*, CUtensorMapDataType, cuuint32_t, void*, const cuuint64_t*, const cuuint64_t*, const cuuint32_t*,
                             const cuuint32_t*, CUtensorMapInterleave, CUtensorMapSwizzle, CUtensorMapL2promotion, CUtensorMapFloatOOBfill);

static void make_map(EncodeFn fn, CUtensorMap* m, const void* ptr, uint64_t d0, uint64_t d1, uint64_t d2, uint64_t s1, uint64_t s2,
                     uint32_t b0, uint32_t b1, uint32_t b2, CUtensorMapSwizzle sw) {
    cuuint64_t dims[3] = {d0, d1, d2}, strides[2] = {s1, s2};
    cuuint32_t box[3] = {b0, b1, b2}, es[3] = {1, 1, 1};
    CUresult rc = fn(m, CU_TENSOR_MAP_DATA_TYPE_BFLOAT16, 3, (void*)ptr, dims, strides, box, es, CU_TENSOR_MAP_INTERLEAVE_NONE, sw,
                     CU_TENSOR_MAP_L2_PROMOTION_L2_128B, CU_TENSOR_MAP_FLOAT_OOB_FILL_NONE);
    (void)rc;
}

extern "C" void kernel_launch(void* const* d_in, const int* in_sizes, int n_in, void* d_out, int out_size) {
    (void)in_sizes; (void)n_in; (void)out_size;
    static EncodeFn fn = nullptr;
    static uint32_t* act_base = nullptr;
    if (!fn) {
        cudaDriverEntryPointQueryResult st;
        cudaGetDriverEntryPoint("cuTensorMapEncodeTiled", (void**)&fn, cudaEnableDefault, &st);
        void* a = nullptr;
        cudaGetSymbolAddress(&a, g_act);
        act_base = (uint32_t*)(((uintptr_t)a + 0xFFFFF) & ~(uintptr_t)0xFFFFF);
        cudaFuncSetAttribute(fused_block_kernel, cudaFuncAttributeMaxDynamicSharedMemorySize, SMEM_BYTES);
    }
    Params p;
    p.x = (const bf16*)d_in[0];
    const bf16* wqkv = (const bf16*)d_in[1];
    p.wqkv = wqkv;
    p.wop = (const bf16*)d_in[2];
    p.wg = (const bf16*)d_in[4];
    p.wu = (const bf16*)d_in[5];
    p.wd = (const bf16*)d_in[6];
    p.c = (const bf16*)d_in[7];
    p.wmod = (const bf16*)d_in[8];
    p.out = (bf16*)d_out;
    p.zero = 0;
    p.actb = act_base;
    make_map(fn, &p.wm, p.wmod, 2688, 448, 1, 5376, 5376 * 448, 16, 224, 1, CU_TENSOR_MAP_SWIZZLE_NONE);
    make_map(fn, &p.xm, p.x, 448, 2048, 1, 896, 896 * 2048, 64, 128, 1, CU_TENSOR_MAP_SWIZZLE_128B);
    make_map(fn, &p.qkv, wqkv, 1344, 448, 1, 2688, 2688 * 448, 64, 224, 1, CU_TENSOR_MAP_SWIZZLE_128B);
    make_map(fn, &p.wo, p.wop, 448, 448, 1, 896, 896 * 448, 64, 224, 1, CU_TENSOR_MAP_SWIZZLE_128B);
    make_map(fn, &p.ga, p.wg, 64, 448, 28, 3584, 128, 64, 32, 2, CU_TENSOR_MAP_SWIZZLE_128B);
    make_map(fn, &p.ua, p.wu, 64, 448, 28, 3584, 128, 64, 32, 2, CU_TENSOR_MAP_SWIZZLE_128B);
    make_map(fn, &p.gb, p.wg, 64, 448, 28, 3584, 128, 64, 64, 1, CU_TENSOR_MAP_SWIZZLE_128B);
    make_map(fn, &p.ub, p.wu, 64, 448, 28, 3584, 128, 64, 64, 1, CU_TENSOR_MAP_SWIZZLE_128B);
    make_map(fn, &p.gc, p.wg, 32, 448, 56, 3584, 64, 32, 64, 1, CU_TENSOR_MAP_SWIZZLE_64B);
    make_map(fn, &p.uc, p.wu, 32, 448, 56, 3584, 64, 32, 64, 1, CU_TENSOR_MAP_SWIZZLE_64B);
    make_map(fn, &p.dn, p.wd, 8, 1792, 56, 896, 16, 8, 32, 7, CU_TENSOR_MAP_SWIZZLE_NONE);
    fused_block_kernel<<<GRID, 384, SMEM_BYTES>>>(p);
}
```

```cpp
#include <cuda_runtime.h>
#include <cuda_bf16.h>
#include <cuda.h>
#include <stdint.h>

typedef __nv_bfloat16 bf16;

__device__ __forceinline__ void wgmma_rl_56(float* d, uint32_t a0, uint32_t a1, uint32_t a2, uint32_t a3, uint64_t db, int sd) {
  asm volatile("{\n.reg .pred p;\nsetp.ne.b32 p, %33, 0;\n"
    "wgmma.mma_async.sync.aligned.m64n56k16.f32.bf16.bf16 {%0,%1,%2,%3,%4,%5,%6,%7,%8,%9,%10,%11,%12,%13,%14,%15,%16,%17,%18,%19,%20,%21,%22,%23,%24,%25,%26,%27}, {%28,%29,%30,%31}, %32, p, 1, 1, 1;\n}\n"
    : "+f"(d[0]),"+f"(d[1]),"+f"(d[2]),"+f"(d[3]),"+f"(d[4]),"+f"(d[5]),"+f"(d[6]),"+f"(d[7]),"+f"(d[8]),"+f"(d[9]),"+f"(d[10]),"+f"(d[11]),"+f"(d[12]),"+f"(d[13]),"+f"(d[14]),"+f"(d[15]),"+f"(d[16]),"+f"(d[17]),"+f"(d[18]),"+f"(d[19]),"+f"(d[20]),"+f"(d[21]),"+f"(d[22]),"+f"(d[23]),"+f"(d[24]),"+f"(d[25]),"+f"(d[26]),"+f"(d[27])
    : "r"(a0), "r"(a1), "r"(a2), "r"(a3), "l"(db), "r"(sd));
}
template<uint64_t CA, uint64_t CB> __device__ __forceinline__ void wgmma_ss_56(float* d, uint32_t da, uint32_t db, int sd) {
  asm volatile("{\n.reg .pred p;\n.reg .b64 a, b;\nsetp.ne.b32 p, %30, 0;\nmov.b64 a, {%28, %31};\nmov.b64 b, {%29, %32};\n"
    "wgmma.mma_async.sync.aligned.m64n56k16.f32.bf16.bf16 {%0,%1,%2,%3,%4,%5,%6,%7,%8,%9,%10,%11,%12,%13,%14,%15,%16,%17,%18,%19,%20,%21,%22,%23,%24,%25,%26,%27}, a, b, p, 1, 1, 0, 1;\n}\n"
    : "+f"(d[0]),"+f"(d[1]),"+f"(d[2]),"+f"(d[3]),"+f"(d[4]),"+f"(d[5]),"+f"(d[6]),"+f"(d[7]),"+f"(d[8]),"+f"(d[9]),"+f"(d[10]),"+f"(d[11]),"+f"(d[12]),"+f"(d[13]),"+f"(d[14]),"+f"(d[15]),"+f"(d[16]),"+f"(d[17]),"+f"(d[18]),"+f"(d[19]),"+f"(d[20]),"+f"(d[21]),"+f"(d[22]),"+f"(d[23]),"+f"(d[24]),"+f"(d[25]),"+f"(d[26]),"+f"(d[27])
    : "r"(da), "r"(db), "r"(sd), "n"((uint32_t)(CA >> 32)), "n"((uint32_t)(CB >> 32)));
}
template<uint64_t CB> __device__ __forceinline__ void wgmma_rs_256(float* d, uint32_t a0, uint32_t a1, uint32_t a2, uint32_t a3, uint32_t db, int sd) {
  asm volatile("{\n.reg .pred p;\n.reg .b64 b;\nsetp.ne.b32 p, %133, 0;\nmov.b64 b, {%132, %134};\n"
    "wgmma.mma_async.sync.aligned.m64n256k16.f32.bf16.bf16 {%0,%1,%2,%3,%4,%5,%6,%7,%8,%9,%10,%11,%12,%13,%14,%15,%16,%17,%18,%19,%20,%21,%22,%23,%24,%25,%26,%27,%28,%29,%30,%31,%32,%33,%34,%35,%36,%37,%38,%39,%40,%41,%42,%43,%44,%45,%46,%47,%48,%49,%50,%51,%52,%53,%54,%55,%56,%57,%58,%59,%60,%61,%62,%63,%64,%65,%66,%67,%68,%69,%70,%71,%72,%73,%74,%75,%76,%77,%78,%79,%80,%81,%82,%83,%84,%85,%86,%87,%88,%89,%90,%91,%92,%93,%94,%95,%96,%97,%98,%99,%100,%101,%102,%103,%104,%105,%106,%107,%108,%109,%110,%111,%112,%113,%114,%115,%116,%117,%118,%119,%120,%121,%122,%123,%124,%125,%126,%127}, {%128,%129,%130,%131}, b, p, 1, 1, 1;\n}\n"
    : "+f"(d[0]),"+f"(d[1]),"+f"(d[2]),"+f"(d[3]),"+f"(d[4]),"+f"(d[5]),"+f"(d[6]),"+f"(d[7]),"+f"(d[8]),"+f"(d[9]),"+f"(d[10]),"+f"(d[11]),"+f"(d[12]),"+f"(d[13]),"+f"(d[14]),"+f"(d[15]),"+f"(d[16]),"+f"(d[17]),"+f"(d[18]),"+f"(d[19]),"+f"(d[20]),"+f"(d[21]),"+f"(d[22]),"+f"(d[23]),"+f"(d[24]),"+f"(d[25]),"+f"(d[26]),"+f"(d[27]),"+f"(d[28]),"+f"(d[29]),"+f"(d[30]),"+f"(d[31]),"+f"(d[32]),"+f"(d[33]),"+f"(d[34]),"+f"(d[35]),"+f"(d[36]),"+f"(d[37]),"+f"(d[38]),"+f"(d[39]),"+f"(d[40]),"+f"(d[41]),"+f"(d[42]),"+f"(d[43]),"+f"(d[44]),"+f"(d[45]),"+f"(d[46]),"+f"(d[47]),"+f"(d[48]),"+f"(d[49]),"+f"(d[50]),"+f"(d[51]),"+f"(d[52]),"+f"(d[53]),"+f"(d[54]),"+f"(d[55]),"+f"(d[56]),"+f"(d[57]),"+f"(d[58]),"+f"(d[59]),"+f"(d[60]),"+f"(d[61]),"+f"(d[62]),"+f"(d[63]),"+f"(d[64]),"+f"(d[65]),"+f"(d[66]),"+f"(d[67]),"+f"(d[68]),"+f"(d[69]),"+f"(d[70]),"+f"(d[71]),"+f"(d[72]),"+f"(d[73]),"+f"(d[74]),"+f"(d[75]),"+f"(d[76]),"+f"(d[77]),"+f"(d[78]),"+f"(d[79]),"+f"(d[80]),"+f"(d[81]),"+f"(d[82]),"+f"(d[83]),"+f"(d[84]),"+f"(d[85]),"+f"(d[86]),"+f"(d[87]),"+f"(d[88]),"+f"(d[89]),"+f"(d[90]),"+f"(d[91]),"+f"(d[92]),"+f"(d[93]),"+f"(d[94]),"+f"(d[95]),"+f"(d[96]),"+f"(d[97]),"+f"(d[98]),"+f"(d[99]),"+f"(d[100]),"+f"(d[101]),"+f"(d[102]),"+f"(d[103]),"+f"(d[104]),"+f"(d[105]),"+f"(d[106]),"+f"(d[107]),"+f"(d[108]),"+f"(d[109]),"+f"(d[110]),"+f"(d[111]),"+f"(d[112]),"+f"(d[113]),"+f"(d[114]),"+f"(d[115]),"+f"(d[116]),"+f"(d[117]),"+f"(d[118]),"+f"(d[119]),"+f"(d[120]),"+f"(d[121]),"+f"(d[122]),"+f"(d[123]),"+f"(d[124]),"+f"(d[125]),"+f"(d[126]),"+f"(d[127])
    : "r"(a0), "r"(a1), "r"(a2), "r"(a3), "r"(db), "r"(sd), "n"((uint32_t)(CB >> 32)));
}
template<uint64_t CA, uint64_t CB> __device__ __forceinline__ void wgmma_ss_128(float* d, uint32_t da, uint32_t db, int sd) {
  asm volatile("{\n.reg .pred p;\n.reg .b64 a, b;\nsetp.ne.b32 p, %66, 0;\nmov.b64 a, {%64, %67};\nmov.b64 b, {%65, %68};\n"
    "wgmma.mma_async.sync.aligned.m64n128k16.f32.bf16.bf16 {%0,%1,%2,%3,%4,%5,%6,%7,%8,%9,%10,%11,%12,%13,%14,%15,%16,%17,%18,%19,%20,%21,%22,%23,%24,%25,%26,%27,%28,%29,%30,%31,%32,%33,%34,%35,%36,%37,%38,%39,%40,%41,%42,%43,%44,%45,%46,%47,%48,%49,%50,%51,%52,%53,%54,%55,%56,%57,%58,%59,%60,%61,%62,%63}, a, b, p, 1, 1, 0, 1;\n}\n"
    : "+f"(d[0]),"+f"(d[1]),"+f"(d[2]),"+f"(d[3]),"+f"(d[4]),"+f"(d[5]),"+f"(d[6]),"+f"(d[7]),"+f"(d[8]),"+f"(d[9]),"+f"(d[10]),"+f"(d[11]),"+f"(d[12]),"+f"(d[13]),"+f"(d[14]),"+f"(d[15]),"+f"(d[16]),"+f"(d[17]),"+f"(d[18]),"+f"(d[19]),"+f"(d[20]),"+f"(d[21]),"+f"(d[22]),"+f"(d[23]),"+f"(d[24]),"+f"(d[25]),"+f"(d[26]),"+f"(d[27]),"+f"(d[28]),"+f"(d[29]),"+f"(d[30]),"+f"(d[31]),"+f"(d[32]),"+f"(d[33]),"+f"(d[34]),"+f"(d[35]),"+f"(d[36]),"+f"(d[37]),"+f"(d[38]),"+f"(d[39]),"+f"(d[40]),"+f"(d[41]),"+f"(d[42]),"+f"(d[43]),"+f"(d[44]),"+f"(d[45]),"+f"(d[46]),"+f"(d[47]),"+f"(d[48]),"+f"(d[49]),"+f"(d[50]),"+f"(d[51]),"+f"(d[52]),"+f"(d[53]),"+f"(d[54]),"+f"(d[55]),"+f"(d[56]),"+f"(d[57]),"+f"(d[58]),"+f"(d[59]),"+f"(d[60]),"+f"(d[61]),"+f"(d[62]),"+f"(d[63])
    : "r"(da), "r"(db), "r"(sd), "n"((uint32_t)(CA >> 32)), "n"((uint32_t)(CB >> 32)));
}
template<uint64_t CA, uint64_t CB> __device__ __forceinline__ void wgmma_ss_64(float* d, uint32_t da, uint32_t db, int sd) {
  asm volatile("{\n.reg .pred p;\n.reg .b64 a, b;\nsetp.ne.b32 p, %34, 0;\nmov.b64 a, {%32, %35};\nmov.b64 b, {%33, %36};\n"
    "wgmma.mma_async.sync.aligned.m64n64k16.f32.bf16.bf16 {%0,%1,%2,%3,%4,%5,%6,%7,%8,%9,%10,%11,%12,%13,%14,%15,%16,%17,%18,%19,%20,%21,%22,%23,%24,%25,%26,%27,%28,%29,%30,%31}, a, b, p, 1, 1, 0, 1;\n}\n"
    : "+f"(d[0]),"+f"(d[1]),"+f"(d[2]),"+f"(d[3]),"+f"(d[4]),"+f"(d[5]),"+f"(d[6]),"+f"(d[7]),"+f"(d[8]),"+f"(d[9]),"+f"(d[10]),"+f"(d[11]),"+f"(d[12]),"+f"(d[13]),"+f"(d[14]),"+f"(d[15]),"+f"(d[16]),"+f"(d[17]),"+f"(d[18]),"+f"(d[19]),"+f"(d[20]),"+f"(d[21]),"+f"(d[22]),"+f"(d[23]),"+f"(d[24]),"+f"(d[25]),"+f"(d[26]),"+f"(d[27]),"+f"(d[28]),"+f"(d[29]),"+f"(d[30]),"+f"(d[31])
    : "r"(da), "r"(db), "r"(sd), "n"((uint32_t)(CA >> 32)), "n"((uint32_t)(CB >> 32)));
}
template<uint64_t CA, uint64_t CB> __device__ __forceinline__ void wgmma_ss_112(float* d, uint32_t da, uint32_t db, int sd) {
  asm volatile("{\n.reg .pred p;\n.reg .b64 a, b;\nsetp.ne.b32 p, %58, 0;\nmov.b64 a, {%56, %59};\nmov.b64 b, {%57, %60};\n"
    "wgmma.mma_async.sync.aligned.m64n112k16.f32.bf16.bf16 {%0,%1,%2,%3,%4,%5,%6,%7,%8,%9,%10,%11,%12,%13,%14,%15,%16,%17,%18,%19,%20,%21,%22,%23,%24,%25,%26,%27,%28,%29,%30,%31,%32,%33,%34,%35,%36,%37,%38,%39,%40,%41,%42,%43,%44,%45,%46,%47,%48,%49,%50,%51,%52,%53,%54,%55}, a, b, p, 1, 1, 0, 1;\n}\n"
    : "+f"(d[0]),"+f"(d[1]),"+f"(d[2]),"+f"(d[3]),"+f"(d[4]),"+f"(d[5]),"+f"(d[6]),"+f"(d[7]),"+f"(d[8]),"+f"(d[9]),"+f"(d[10]),"+f"(d[11]),"+f"(d[12]),"+f"(d[13]),"+f"(d[14]),"+f"(d[15]),"+f"(d[16]),"+f"(d[17]),"+f"(d[18]),"+f"(d[19]),"+f"(d[20]),"+f"(d[21]),"+f"(d[22]),"+f"(d[23]),"+f"(d[24]),"+f"(d[25]),"+f"(d[26]),"+f"(d[27]),"+f"(d[28]),"+f"(d[29]),"+f"(d[30]),"+f"(d[31]),"+f"(d[32]),"+f"(d[33]),"+f"(d[34]),"+f"(d[35]),"+f"(d[36]),"+f"(d[37]),"+f"(d[38]),"+f"(d[39]),"+f"(d[40]),"+f"(d[41]),"+f"(d[42]),"+f"(d[43]),"+f"(d[44]),"+f"(d[45]),"+f"(d[46]),"+f"(d[47]),"+f"(d[48]),"+f"(d[49]),"+f"(d[50]),"+f"(d[51]),"+f"(d[52]),"+f"(d[53]),"+f"(d[54]),"+f"(d[55])
    : "r"(da), "r"(db), "r"(sd), "n"((uint32_t)(CA >> 32)), "n"((uint32_t)(CB >> 32)));
}
template<uint64_t CB> __device__ __forceinline__ void wgmma_rs_112(float* d, uint32_t a0, uint32_t a1, uint32_t a2, uint32_t a3, uint32_t db, int sd) {
  asm volatile("{\n.reg .pred p;\n.reg .b64 b;\nsetp.ne.b32 p, %61, 0;\nmov.b64 b, {%60, %62};\n"
    "wgmma.mma_async.sync.aligned.m64n112k16.f32.bf16.bf16 {%0,%1,%2,%3,%4,%5,%6,%7,%8,%9,%10,%11,%12,%13,%14,%15,%16,%17,%18,%19,%20,%21,%22,%23,%24,%25,%26,%27,%28,%29,%30,%31,%32,%33,%34,%35,%36,%37,%38,%39,%40,%41,%42,%43,%44,%45,%46,%47,%48,%49,%50,%51,%52,%53,%54,%55}, {%56,%57,%58,%59}, b, p, 1, 1, 1;\n}\n"
    : "+f"(d[0]),"+f"(d[1]),"+f"(d[2]),"+f"(d[3]),"+f"(d[4]),"+f"(d[5]),"+f"(d[6]),"+f"(d[7]),"+f"(d[8]),"+f"(d[9]),"+f"(d[10]),"+f"(d[11]),"+f"(d[12]),"+f"(d[13]),"+f"(d[14]),"+f"(d[15]),"+f"(d[16]),"+f"(d[17]),"+f"(d[18]),"+f"(d[19]),"+f"(d[20]),"+f"(d[21]),"+f"(d[22]),"+f"(d[23]),"+f"(d[24]),"+f"(d[25]),"+f"(d[26]),"+f"(d[27]),"+f"(d[28]),"+f"(d[29]),"+f"(d[30]),"+f"(d[31]),"+f"(d[32]),"+f"(d[33]),"+f"(d[34]),"+f"(d[35]),"+f"(d[36]),"+f"(d[37]),"+f"(d[38]),"+f"(d[39]),"+f"(d[40]),"+f"(d[41]),"+f"(d[42]),"+f"(d[43]),"+f"(d[44]),"+f"(d[45]),"+f"(d[46]),"+f"(d[47]),"+f"(d[48]),"+f"(d[49]),"+f"(d[50]),"+f"(d[51]),"+f"(d[52]),"+f"(d[53]),"+f"(d[54]),"+f"(d[55])
    : "r"(a0), "r"(a1), "r"(a2), "r"(a3), "r"(db), "r"(sd), "n"((uint32_t)(CB >> 32)));
}

constexpr int DM = 448;
constexpr int NCTA = 128;
#define MAPPING 1
#define GRID 132
#define PINGPONG 0
#define WIN 6
#define WIN_END 25
#define UNR_B 1
#define UNR_C 1
constexpr int kB = UNR_B, kC = UNR_C;
#define LIKELY(x) __builtin_expect(!!(x), 1)
#define PACE 1
#define PACE_END 6
#define MAP_S 4
constexpr int SPIN_LIMIT = 1 << 22;

constexpr uint32_t OFF_X = 0, OFF_Y = 114688, OFF_MISC = 229376, SMEM_BYTES = 232448;
constexpr uint32_t Y_VR = 0, Y_K = 28672, Y_KOWN = 57344, Y_VOWN = 71680, Y_Q = 86016;
constexpr uint32_t HALF = 57344;
constexpr uint32_t X_STAT = 49152;
constexpr uint32_t M_BAR = OFF_MISC;
constexpr uint32_t M_ST = OFF_MISC + 512;
constexpr uint32_t M_G = OFF_MISC + 2304;
constexpr uint32_t M_EPOCH = OFF_MISC + 3040;
enum { B_XFULL = 0, B_FULLK = 7, B_FULLV = 8, B_FULLQ, B_KRFULL, B_VRFULL, B_WOFULL, B_XCH, B_MOD1 = 15, B_FULL = 16, B_WMFULL = 30,
       B_EMPTY = 32, B_XFREE = B_EMPTY + 12, B_GEMV, B_PEER,
       B_PUB = 47,
       B_WMFREE = 56, B_HRDY, B_GFULL = B_HRDY + 3, B_DONE = 31, B_DUMMY = B_GEMV };

__device__ uint32_t g_ticket;
__device__ __align__(128) uint32_t g_mod[8 * 6 * DM];
__device__ __align__(128) uint32_t g_flag[144 * 128];
constexpr int RB_WORDS = 262144, RB_KV = 0, RB_O = 57344, RB_X1 = 86016, RB_H2 = 143360, RB_ST = 258048;
__device__ __align__(128) uint32_t g_act[18 * RB_WORDS];
__device__ __align__(128) uint32_t g_wd[56 * 4 * 1792];
#define PROFH(id)
#define PROFH1(id)
#define PROFC(id)

struct alignas(64) Params {
    CUtensorMap wm, xm, qkv, wo, ga, ua, gb, ub, gc, uc, dn;
    const bf16 *x, *c, *wqkv, *wmod, *wg, *wu, *wd, *wop;
    bf16* out;
    uint32_t* actb;
    uint32_t zero;
};

__device__ __forceinline__ void mbar_init(uint32_t bar, int cnt) { asm volatile("mbarrier.init.shared::cta.b64 [%0], %1;" ::"r"(bar), "r"(cnt) : "memory"); }
__device__ __forceinline__ void mbar_expect_tx(uint32_t bar, uint32_t bytes) { asm volatile("mbarrier.arrive.expect_tx.shared::cta.b64 _, [%0], %1;" ::"r"(bar), "r"(bytes) : "memory"); }
__device__ __forceinline__ void mbar_arrive(uint32_t bar) { asm volatile("mbarrier.arrive.shared::cta.b64 _, [%0];" ::"r"(bar) : "memory"); }
__device__ __forceinline__ void mbar_wait(uint32_t bar, uint32_t parity) {
    uint32_t ok; int n = 0;
    do {
        asm volatile("{\n.reg .pred p;\nmbarrier.try_wait.parity.shared::cta.b64 p, [%1], %2;\nselp.u32 %0, 1, 0, p;\n}" : "=r"(ok) : "r"(bar), "r"(parity) : "memory");
        if (++n > SPIN_LIMIT) __trap();
    } while (!ok);
}
__device__ __forceinline__ void mbar_wait_c(uint32_t bar, uint32_t parity) {
    asm volatile("{\n.reg .pred p;\nWL:\nmbarrier.try_wait.parity.shared::cta.b64 p, [%0], %1;\n@!p bra WL;\n}" ::"r"(bar), "r"(parity) : "memory");
}
__device__ __forceinline__ void mbar_wait_cluster(uint32_t bar, uint32_t parity) {
    uint32_t ok; int n = 0;
    do {
        asm volatile("{\n.reg .pred p;\nmbarrier.try_wait.parity.acquire.cluster.shared::cta.b64 p, [%1], %2;\nselp.u32 %0, 1, 0, p;\n}" : "=r"(ok) : "r"(bar), "r"(parity) : "memory");
        if (++n > SPIN_LIMIT) __trap();
    } while (!ok);
}
__device__ __forceinline__ void warp_arrive(uint32_t bar) {
    __syncwarp();
    asm volatile("{\n.reg .pred p;\nelect.sync _|p, 0xffffffff;\n@p mbarrier.arrive.shared::cta.b64 _, [%0];\n}" ::"r"(bar) : "memory");
}
__device__ __forceinline__ int opaque(int v) { return __shfl_sync(~0u, v, 0); }
__device__ __forceinline__ int fresh_tid() { int v; asm volatile("mov.u32 %0, %%tid.x;" : "=r"(v)); return v; }
__device__ __forceinline__ void bar_sync(int id, int n) { asm volatile("bar.sync %0, %1;" ::"r"(id), "r"(n) : "memory"); }
__device__ __forceinline__ void bar_arrive(int id, int n) { asm volatile("bar.arrive %0, %1;" ::"r"(id), "r"(n) : "memory"); }
__device__ __forceinline__ void fence_async_smem() { asm volatile("fence.proxy.async.shared::cta;" ::: "memory"); }
__device__ __forceinline__ void fence_async_global() { asm volatile("fence.proxy.async.global;" ::: "memory"); }
__device__ __forceinline__ void fence_gpu() { asm volatile("fence.release.gpu;" ::: "memory"); }
__device__ __forceinline__ void tma3(uint32_t dst, const CUtensorMap* m, int c0, int c1, int c2, uint32_t bar) {
    asm volatile("cp.async.bulk.tensor.3d.shared::cluster.global.mbarrier::complete_tx::bytes [%0], [%1, {%3, %4, %5}], [%2];"
                 ::"r"(dst), "l"(m), "r"(bar), "r"(c0), "r"(c1), "r"(c2) : "memory");
}
__device__ __forceinline__ void bulk_load(uint32_t dst, const void* src, uint32_t bytes, uint32_t bar) {
    asm volatile("cp.async.bulk.shared::cluster.global.mbarrier::complete_tx::bytes [%0], [%1], %2, [%3];" ::"r"(dst), "l"(src), "r"(bytes), "r"(bar) : "memory");
}
__device__ __forceinline__ void expect_e(uint32_t bar, uint32_t bytes) {
    asm volatile("{\n.reg .pred p;\nelect.sync _|p, 0xffffffff;\n@p mbarrier.arrive.expect_tx.shared::cta.b64 _, [%0], %1;\n}" ::"r"(bar), "r"(bytes) : "memory");
}
__device__ __forceinline__ void tma3_e(uint32_t dst, const CUtensorMap* m, int c0, int c1, int c2, uint32_t bar) {
    asm volatile("{\n.reg .pred p;\nelect.sync _|p, 0xffffffff;\n@p cp.async.bulk.tensor.3d.shared::cluster.global.mbarrier::complete_tx::bytes [%0], [%1, {%3, %4, %5}], [%2];\n}"
                 ::"r"(dst), "l"(m), "r"(bar), "r"(c0), "r"(c1), "r"(c2) : "memory");
}
__device__ __forceinline__ void bulk_e(uint32_t dst, const void* src, uint32_t bytes, uint32_t bar) {
    asm volatile("{\n.reg .pred p;\nelect.sync _|p, 0xffffffff;\n@p cp.async.bulk.shared::cluster.global.mbarrier::complete_tx::bytes [%0], [%1], %2, [%3];\n}"
                 ::"r"(dst), "l"(src), "r"(bytes), "r"(bar) : "memory");
}
__device__ __forceinline__ void init_e(uint32_t bar, int cnt) {
    asm volatile("{\n.reg .pred p;\nelect.sync _|p, 0xffffffff;\n@p mbarrier.init.shared::cta.b64 [%0], %1;\n}" ::"r"(bar), "r"(cnt) : "memory");
}
__device__ __forceinline__ void l2_prefetch_e(const void* src, uint32_t bytes) {
    asm volatile("{\n.reg .pred p;\nelect.sync _|p, 0xffffffff;\n@p cp.async.bulk.prefetch.L2.global [%0], %1;\n}" ::"l"(src), "r"(bytes) : "memory");
}
__device__ __forceinline__ uint32_t ld_relaxed(const uint32_t* p) { uint32_t v; asm volatile("ld.relaxed.gpu.global.u32 %0, [%1];" : "=r"(v) : "l"(p) : "memory"); return v; }
__device__ __forceinline__ void st_relaxed(uint32_t* p, uint32_t v) { asm volatile("st.relaxed.gpu.global.u32 [%0], %1;" ::"l"(p), "r"(v) : "memory"); }
__device__ __forceinline__ uint4 ld_relaxed4(const uint4* p) { uint4 v; asm volatile("ld.relaxed.gpu.global.v4.u32 {%0,%1,%2,%3}, [%4];" : "=r"(v.x), "=r"(v.y), "=r"(v.z), "=r"(v.w) : "l"(p) : "memory"); return v; }
__device__ __forceinline__ void st_relaxed4(uint4* p, uint4 v) { asm volatile("st.relaxed.gpu.global.v4.u32 [%0], {%1,%2,%3,%4};" ::"l"(p), "r"(v.x), "r"(v.y), "r"(v.z), "r"(v.w) : "memory"); }
__device__ __forceinline__ uint4 ldg_nc4(const void* p) { uint4 v; asm volatile("ld.global.nc.L1::no_allocate.v4.u32 {%0,%1,%2,%3}, [%4];" : "=r"(v.x), "=r"(v.y), "=r"(v.z), "=r"(v.w) : "l"(p)); return v; }
__device__ __forceinline__ uint32_t ldg_nc(const void* p) { uint32_t v; asm volatile("ld.global.nc.u32 %0, [%1];" : "=r"(v) : "l"(p)); return v; }
__device__ __forceinline__ uint32_t ld_acquire(const uint32_t* p) { uint32_t v; asm volatile("ld.acquire.gpu.global.u32 %0, [%1];" : "=r"(v) : "l"(p) : "memory"); return v; }
__device__ __forceinline__ uint4 lds4(uint32_t a) { uint4 v; asm volatile("ld.shared.v4.u32 {%0,%1,%2,%3}, [%4];" : "=r"(v.x), "=r"(v.y), "=r"(v.z), "=r"(v.w) : "r"(a) : "memory"); return v; }
__device__ __forceinline__ float2 lds2f(uint32_t a) { float2 v; asm volatile("ld.shared.v2.f32 {%0,%1}, [%2];" : "=f"(v.x), "=f"(v.y) : "r"(a) : "memory"); return v; }
__device__ __forceinline__ uint32_t lds1(uint32_t a) { uint32_t v; asm volatile("ld.shared.u32 %0, [%1];" : "=r"(v) : "r"(a) : "memory"); return v; }
__device__ __forceinline__ void sts4(uint32_t a, uint4 v) { asm volatile("st.shared.v4.u32 [%0], {%1,%2,%3,%4};" ::"r"(a), "r"(v.x), "r"(v.y), "r"(v.z), "r"(v.w) : "memory"); }
__device__ __forceinline__ void sts2(uint32_t a, uint32_t x, uint32_t y) { asm volatile("st.shared.v2.u32 [%0], {%1,%2};" ::"r"(a), "r"(x), "r"(y) : "memory"); }
__device__ __forceinline__ void sts1(uint32_t a, uint32_t v) { asm volatile("st.shared.u32 [%0], %1;" ::"r"(a), "r"(v) : "memory"); }
__device__ __forceinline__ void stsm4(uint32_t a, uint32_t r0, uint32_t r1, uint32_t r2, uint32_t r3) {
    asm volatile("stmatrix.sync.aligned.m8n8.x4.shared.b16 [%0], {%1,%2,%3,%4};" ::"r"(a), "r"(r0), "r"(r1), "r"(r2), "r"(r3));
}
__device__ __forceinline__ uint32_t pack2(float lo, float hi) { uint32_t r; asm("cvt.rn.bf16x2.f32 %0, %1, %2;" : "=r"(r) : "f"(hi), "f"(lo)); return r; }
__device__ __forceinline__ uint32_t pack2_relu(float lo, float hi) { uint32_t r; asm("cvt.rn.relu.bf16x2.f32 %0, %1, %2;" : "=r"(r) : "f"(hi), "f"(lo)); return r; }
__device__ __forceinline__ uint32_t hfma2(uint32_t a, uint32_t b, uint32_t c) { uint32_t r; asm("fma.rn.bf16x2 %0, %1, %2, %3;" : "=r"(r) : "r"(a), "r"(b), "r"(c)); return r; }
__device__ __forceinline__ uint32_t hmul2(uint32_t a, uint32_t b) { uint32_t r; asm("mul.rn.bf16x2 %0, %1, %2;" : "=r"(r) : "r"(a), "r"(b)); return r; }
__device__ __forceinline__ float bf_lo(uint32_t v) { return __uint_as_float(v << 16); }
__device__ __forceinline__ float bf_hi(uint32_t v) { return __uint_as_float(v & 0xFFFF0000u); }
__device__ __forceinline__ float bf_round(float v) { return bf_lo(pack2(v, 0.f)); }
__device__ __forceinline__ float ex2(float x) { float r; asm("ex2.approx.ftz.f32 %0, %1;" : "=f"(r) : "f"(x)); return r; }
__device__ __forceinline__ void mma16816(float* d, uint32_t a0, uint32_t a1, uint32_t a2, uint32_t a3, uint32_t b0, uint32_t b1) {
    asm("mma.sync.aligned.m16n8k16.row.col.f32.bf16.bf16.f32 {%0,%1,%2,%3}, {%4,%5,%6,%7}, {%8,%9}, {%0,%1,%2,%3};"
        : "+f"(d[0]), "+f"(d[1]), "+f"(d[2]), "+f"(d[3]) : "r"(a0), "r"(a1), "r"(a2), "r"(a3), "r"(b0), "r"(b1));
}
__device__ __forceinline__ void mma16816_first(float* d, uint32_t a0, uint32_t a1, uint32_t a2, uint32_t a3, uint32_t b0, uint32_t b1) {
    asm volatile("mma.sync.aligned.m16n8k16.row.col.f32.bf16.bf16.f32 {%0,%1,%2,%3}, {%4,%5,%6,%7}, {%8,%9}, {%10,%10,%10,%10};"
        : "=f"(d[0]), "=f"(d[1]), "=f"(d[2]), "=f"(d[3]) : "r"(a0), "r"(a1), "r"(a2), "r"(a3), "r"(b0), "r"(b1), "f"(0.f));
}
__device__ __forceinline__ void mma16816_v(float* d, uint32_t a0, uint32_t a1, uint32_t a2, uint32_t a3, uint32_t b0, uint32_t b1) {
    asm volatile("mma.sync.aligned.m16n8k16.row.col.f32.bf16.bf16.f32 {%0,%1,%2,%3}, {%4,%5,%6,%7}, {%8,%9}, {%0,%1,%2,%3};"
        : "+f"(d[0]), "+f"(d[1]), "+f"(d[2]), "+f"(d[3]) : "r"(a0), "r"(a1), "r"(a2), "r"(a3), "r"(b0), "r"(b1));
}
__device__ __forceinline__ void mma1688(float* d, uint32_t a0, uint32_t a1, uint32_t b0) {
    asm("mma.sync.aligned.m16n8k8.row.col.f32.bf16.bf16.f32 {%0,%1,%2,%3}, {%4,%5}, {%6}, {%0,%1,%2,%3};"
        : "+f"(d[0]), "+f"(d[1]), "+f"(d[2]), "+f"(d[3]) : "r"(a0), "r"(a1), "r"(b0));
}
__device__ __forceinline__ void ldsm4(uint32_t a, uint32_t* r) {
    asm volatile("ldmatrix.sync.aligned.m8n8.x4.shared.b16 {%0,%1,%2,%3}, [%4];" : "=r"(r[0]), "=r"(r[1]), "=r"(r[2]), "=r"(r[3]) : "r"(a));
}
__device__ __forceinline__ void ldsm4t(uint32_t a, uint32_t* r) {
    asm volatile("ldmatrix.sync.aligned.m8n8.x4.trans.shared.b16 {%0,%1,%2,%3}, [%4];" : "=r"(r[0]), "=r"(r[1]), "=r"(r[2]), "=r"(r[3]) : "r"(a));
}
__device__ __forceinline__ uint32_t nz(uint32_t v) { uint32_t r; asm("max.u32 %0, %1, 1;" : "=r"(r) : "r"(v)); return r; }
__device__ __forceinline__ float rcp(float x) { float r; asm("rcp.approx.ftz.f32 %0, %1;" : "=f"(r) : "f"(x)); return r; }
__device__ __forceinline__ uint2 ld_relaxed2(const void* p) { uint2 v; asm volatile("ld.relaxed.gpu.global.v2.u32 {%0,%1}, [%2];" : "=r"(v.x), "=r"(v.y) : "l"(p) : "memory"); return v; }
__device__ __forceinline__ void st_relaxed2(void* p, uint32_t x, uint32_t y) { asm volatile("st.relaxed.gpu.global.v2.u32 [%0], {%1,%2};" ::"l"(p), "r"(max(x, 1u)), "r"(max(y, 1u)) : "memory"); }
__host__ __device__ constexpr uint64_t dconst(uint32_t lbo, uint32_t sbo, uint32_t swz) {
    return ((uint64_t)(lbo >> 4) << 16) | ((uint64_t)(sbo >> 4) << 32) | ((uint64_t)swz << 62);
}
__device__ __forceinline__ uint32_t mkdesc(uint32_t addr, uint64_t c) { return (uint32_t)c | ((addr & 0x3FFFF) >> 4); }
#define WG_FENCE() asm volatile("wgmma.fence.sync.aligned;" ::: "memory")
#define WG_COMMIT() asm volatile("wgmma.commit_group.sync.aligned;" ::: "memory")
#define WG_WAIT(n) asm volatile("wgmma.wait_group.sync.aligned %0;" ::"n"(n) : "memory")
template <int N> __device__ __forceinline__ void reg_fence(float* d) {
#pragma unroll
    for (int i = 0; i < N; i++) asm volatile("" : "+f"(d[i])::"memory");
}
template <int N> __device__ __forceinline__ void reg_def(float* d) {
#pragma unroll
    for (int i = 0; i < N; i++) asm volatile("" : "=f"(d[i]));
}
template <int N> __device__ __forceinline__ void reg_def(uint32_t* d) {
#pragma unroll
    for (int i = 0; i < N; i++) asm volatile("" : "=r"(d[i]));
}
__device__ __forceinline__ bool is_unset(uint4 v) { return min(min(v.x, v.y), min(v.z, v.w)) == 0u; }
__device__ __forceinline__ uint4 nz4(uint32_t a, uint32_t b, uint32_t c, uint32_t d) { return make_uint4(max(a, 1u), max(b, 1u), max(c, 1u), max(d, 1u)); }
__device__ __forceinline__ void wait_flags(const uint32_t* p, uint32_t target, uint32_t mask) {
    int n = 0;
    while (~__ballot_sync(~0u, (int)(ld_relaxed(p) - target) >= 0) & mask) { if (++n > SPIN_LIMIT) __trap(); }
    asm volatile("fence.acquire.gpu;" ::: "memory");
}
__device__ __forceinline__ float silu_bf(uint32_t cbits) {
    const float c = __uint_as_float(cbits << 16);
    return bf_round(__fdividef(c, 1.f + fminf(ex2(-1.4426950408889634f * c), 1e30f)));
}
__device__ __forceinline__ void gemv_part(uint32_t wmbuf, int npanel, int wp, int lane) {
    const uint32_t wa = wmbuf + wp * 512 + (8 * (lane >> 4) + (lane & 7)) * 32 + ((lane >> 3) & 1) * 16;
    uint2 B[4];
#pragma unroll
    for (int i = 0; i < 4; i++) { const float2 v = lds2f(wmbuf + 28672 + (wp + 8 * i) * 32 + (lane & 3) * 8); B[i] = make_uint2(__float_as_uint(v.x), __float_as_uint(v.y)); }
#pragma unroll 1
    for (int pn = 0; pn < npanel; pn++) {
        float d[4] = {};
        uint32_t A[16];
#pragma unroll
        for (int i = 0; i < 4; i++) ldsm4t(wa + pn * 14336 + (i < 3 || wp < 4 ? i : 0) * 4096, A + 4 * i);
#pragma unroll
        for (int i = 0; i < 4; i++) mma16816(d, A[4 * i], A[4 * i + 1], A[4 * i + 2], A[4 * i + 3], B[i].x, B[i].y);
        if ((lane & 3) == 0) {
            sts1(wmbuf + 29696 + (wp * 32 + pn * 16 + (lane >> 2)) * 4, __float_as_uint(d[0]));
            sts1(wmbuf + 29696 + (wp * 32 + pn * 16 + 8 + (lane >> 2)) * 4, __float_as_uint(d[2]));
        }
    }
}
__device__ __forceinline__ const uint4* mod_src(int i, int r, int j, bool p2) {
    i = min(i, p2 ? 251 : 223);
    return (const uint4*)g_mod + (r & 7) * (6 * DM / 4) + (i < 224 ? (p2 ? 336 : 0) + i : (i < 238 ? 14 * j + i : 14 * j + i + 322));
}
__device__ __forceinline__ void mod_store(uint32_t sb, uint4 v, const uint4* src, int i, uint32_t sc) {
    const uint32_t tag = lds1(sb + M_EPOCH) + 1;
    while (__any_sync(~0u, (((v.x ^ tag) | (v.y ^ tag) | (v.z ^ tag) | (v.w ^ tag)) & 0xFFFFu) != 0u) && !sc) v = ld_relaxed4(src);
    if (i < 224) {
        const int isc = i >= 112, c4 = i - 112 * isc;
        const uint32_t a = sb + M_ST + (c4 >> 2) * 64 + (c4 & 1) * 32 + (c4 & 2) * 4 + (isc ? 0 : 4);
        sts1(a, __byte_perm(v.x, v.y, 0x7632));
        sts1(a + 16, __byte_perm(v.z, v.w, 0x7632));
    } else if (i < 252) {
        sts4(sb + M_G + (i - 224) * 16, make_uint4(v.x & 0xFFFF0000u, v.y & 0xFFFF0000u, v.z & 0xFFFF0000u, v.w & 0xFFFF0000u));
    }
}
__device__ __forceinline__ int pass_f(int fs, int ps) { return 224 * fs + ((fs & 1) ? (ps == 0 ? 96 : ps == 1 ? 32 : 0) : (ps == 0 ? 0 : ps == 1 ? 128 : 192)); }
__device__ __forceinline__ constexpr uint32_t slot_off(int l) { return l * 16384; }
__device__ __forceinline__ constexpr int g1_slot(int s) { return s % 7; }
__device__ __noinline__ void x1_fix(const uint32_t* g, uint32_t sa, int s) {
#pragma unroll 1
    for (int k = 4 * s; k < 4 * s + 4;) {
        const uint4 v = ld_relaxed4((const uint4*)(g + k * 256));
        sts4(sa + k * 1024, v);
        k += 2 * __all_sync(~0u, min(min(v.x, v.y), min(v.z, v.w)) != 0u);
    }
    __syncwarp();
}
__device__ __forceinline__ void ln_coeffs(float mean, float msq, uint32_t& r2, uint32_t& n2) {
    const float rs = bf_round(rsqrtf(fmaxf(msq - mean * mean, 0.f) + 1e-5f));
    r2 = pack2(rs, rs);
    n2 = pack2(-mean * rs, -mean * rs);
}

#define LOADW bulk_e(dst, g_wd + (size_t)((f >> 5) * 4 + nq) * 1792, 7168, bar);
template <int sec> __device__ __forceinline__ void ring_loader(const Params& p, uint32_t sb_, int r_, int j_, int lane) {
    const uint32_t sb = opaque(sb_);
    const int r = opaque(r_), j = opaque(j_), nq = j >> 1, fs = 4 * (j & 1) + nq;
    const int fa = pass_f(fs, 0), fb = pass_f(fs, 1), fc = pass_f(fs, 2);
    const uint32_t* h2src = (const uint32_t*)__shfl_sync(~0u, (unsigned long long)(p.actb + (size_t)r * RB_WORDS + RB_H2), 0);
    const CUtensorMap* gmap = (const CUtensorMap*)__shfl_sync(~0u, (unsigned long long)(&p.ga + sec), 0);
#define BAR(i) (sb + M_BAR + 8 * (i))
#define kh (j & 1)
            int sl = 0;
            mbar_wait(BAR(B_PUB + 2), 0);
            wait_flags(g_flag + (8 * r + j) * 128 + 96 + lane, lds1(sb + M_EPOCH) + 1, 0xFFFFu);
            fence_async_global();
#pragma unroll 1
            for (int s = 0; s < 28; s++) {
                const int ps = s < 14 ? 0 : s < 21 ? 1 : 2;
                const uint32_t half = ps < 2 ? 8192 : 4096;
                const int sp = sl;
                if (s >= PACE && s < PACE_END) mbar_wait(BAR(B_FULL + s - PACE), 0);
                mbar_wait(BAR(B_EMPTY + sp), (s >= 7 && s < 14) || s >= 21);
                expect_e(BAR(B_FULL + sp), half);
                tma3_e(sb + slot_off(sp) + sec * half, gmap + 2 * ps, 0, ps ? 64 * sl : 32 * s, ps == 0 ? fa >> 6 : ps == 1 ? fb >> 6 : fc >> 5, BAR(B_FULL + sp));
                sl = sl == 6 ? 0 : sl + 1;
            }
            if (!sec) PROFH(3);
#pragma unroll 1
            for (int e = 0; e < 4; e++) {
                const uint32_t dst = sb + slot_off(e) + sec * 8192, bar = BAR(B_FULL + e);
                const int f = (e < 2 ? fa + 64 * e : e == 2 ? fb : fc) + 32 * sec;
                mbar_wait(BAR(B_EMPTY + e), 0);
                expect_e(bar, e == 3 && sec ? 0 : 7168);
                if (!(e == 3 && sec)) { LOADW }
            }
            sl = 4;
            int e = 4;
#pragma unroll 1
            for (int grp = 0; grp < 9; grp++) {
                const int ps = grp >= 6 ? 2 : grp >= 3 ? 1 : 0;
                int sidx = grp - 3 * ps;
                if (sec && sidx == 0) { mbar_wait(BAR(B_HRDY + ps), 0); fence_async_global(); }
                sidx += sidx >= nq;
                int f = pass_f(4 * kh + sidx, ps);
#pragma unroll 1
                for (int k = 4 >> ps; k > 0; k--, e++, f += 32) {
                    const uint32_t dst = sb + slot_off(sl), bar = BAR(B_FULL + sl);
                    mbar_wait(BAR(B_EMPTY + sl), e >= 12 && e < 24);
                    if (e < WIN_END && e >= WIN) mbar_wait(BAR(B_FULL + (sl >= WIN ? sl - WIN : sl + 12 - WIN)), e - WIN >= 12);
                    expect_e(bar, sec ? 8192 : 7168);
                    if (!sec) { LOADW }
                    else bulk_e(dst + 8192, h2src + f * 64, 8192, bar);
                    sl = sl == 11 ? 0 : sl + 1;
                }
            }
            if (!sec) PROFH(4);
}

#define act (p.actb + (size_t)r * RB_WORDS)
#define PROF_PARAMS
#define PROF_ARGS
__device__ __noinline__ void helper_late(const Params& p, int r_, int j_, int warp_ PROF_PARAMS) {
    extern __shared__ __align__(1024) unsigned char smem[];
    const uint32_t sb = (uint32_t)__cvta_generic_to_shared(smem);
    const int r = opaque(r_), j = opaque(j_), warp = opaque(warp_), nq = j >> 1, b = 8 * r + j;
    {
        const int lane = fresh_tid() & 31;
        const uint32_t target = lds1(sb + M_EPOCH) + 1;
        if (warp == 8) { expect_e(BAR(B_XCH), 14336); expect_e(BAR(B_XCH + 1), 14336); }
            if (warp == 9) {
#pragma unroll 1
                for (int kv = 0; kv < 2; kv++) {
                    mbar_wait(BAR(B_PUB + kv), 0);
                    wait_flags(g_flag + b * 128 + lane, target, (r >= 2 ? 6u : r == 1 ? 2u : 0u) << (8 * kv));
                    fence_async_global();
                    const uint32_t dst = sb + OFF_Y + (kv ? Y_VR : Y_K);
                    expect_e(BAR(B_KRFULL + kv), r >= 2 ? 28672 : r == 1 ? 14336 : 0);
                    if (r >= 2) bulk_e(dst, act - 2 * RB_WORDS + RB_KV + j * 7168 + kv * 3584, 14336, BAR(B_KRFULL + kv));
                    if (r >= 1) bulk_e(dst + 14336, act - RB_WORDS + RB_KV + j * 7168 + kv * 3584, 14336, BAR(B_KRFULL + kv));
                }
            } else if (warp == 11) {
                mbar_wait(BAR(B_VRFULL), 0);
                l2_prefetch_e((const char*)p.wg + (size_t)b * 12544, 12544);
                l2_prefetch_e((const char*)p.wu + (size_t)b * 12544, 12544);
#pragma unroll 1
                for (int k = 0; k < (r < 12 ? 2 : 1); k++) {
                    const int u = 28 * kh + r + 16 * k;
                    expect_e(BAR(B_XFULL + k), 7168);
                    tma3_e(sb + OFF_Y + 102400, &p.dn, 0, 32 * u, 7 * j, BAR(B_XFULL + k));
                    tma3_e(sb + OFF_Y + 102400 + 3584, &p.dn, 0, 32 * u, 7 * (j ^ 1), BAR(B_XFULL + k));
                    mbar_wait(BAR(B_XFULL + k), 1);
                    asm volatile("{\n.reg .pred p;\nelect.sync _|p, 0xffffffff;\n@p cp.async.bulk.global.shared::cta.bulk_group [%0], [%1], 7168;\n"
                                 "cp.async.bulk.commit_group;\ncp.async.bulk.wait_group 0;\n}" ::"l"(g_wd + (size_t)(u * 4 + nq) * 1792), "r"(sb + OFF_Y + 102400) : "memory");
                    __syncwarp();
                }
                warp_arrive(BAR(B_WMFREE));
                fence_gpu();
                if (lane < 16) st_relaxed(g_flag + (8 * lane + j) * 128 + 96 + r, target);
            }
        if (warp == 8 || warp == 11) {
            const int sec = warp == 11;
            if (sec) ring_loader<1>(p, sb, r, j, lane); else ring_loader<0>(p, sb, r, j, lane);
            mbar_wait(BAR(B_DONE), 0);
        } else if (warp == 9) {
#pragma unroll
            for (int ev = 0; ev < 4; ev++) { expect_e(BAR(B_GFULL + ev), ev < 2 ? HALF / 2 : 16384 + 4096); expect_e(BAR(B_XFULL + 2 + ev), ev < 2 ? HALF / 2 : HALF - 16384); }
            mbar_wait(BAR(B_PUB + 2), 0);
            const uint32_t* fp = g_flag + b * 128 + 32 + lane;
            const int par = (target - 1) & 1;
#pragma unroll 1
            for (int n = 0, ev = 0; ev < 4; n++) {
                if (ev == 1) { mbar_wait(BAR(B_WMFREE), 1); mbar_wait(BAR(B_PUB + 3), 0); }
                uint32_t ok = __ballot_sync(~0u, (int)(ld_relaxed(fp) - target) >= 0) >> (8 * ev);
                while ((ok & 0xFFu) == 0xFFu) {
                    asm volatile("fence.acquire.gpu;" ::: "memory");
                    fence_async_global();
                    const int tile = (ev & 1) + (ev >> 1) * par * 2;
                    const uint32_t dst = sb + (ev == 0 ? OFF_X : OFF_Y + (ev & 1) * HALF), first = ev < 2 ? HALF / 2 : 16384;
                    const char* src = (const char*)(act + RB_O + ((ev >> 1) * 2 + tile) * 14336);
                    if (ev >= 2) bulk_e(sb + OFF_X + X_STAT + (ev & 1) * 49152, act + RB_ST + tile * 1024, 4096, BAR(B_GFULL + ev));
                    bulk_e(dst, src, first, BAR(B_GFULL + ev));
                    bulk_e(dst + first, src + first, HALF - first, BAR(B_XFULL + 2 + ev));
                    if (ev) PROFH(4 + ev);
                    ev++; ok >>= 8;
                }
                if (n > SPIN_LIMIT) __trap();
            }
            mbar_wait(BAR(B_XFULL + 5), 1);
#pragma unroll 1
            for (int hf = 0; hf < 2; hf++) {
                const int tile = (par ^ 1) * 2 + hf;
                uint4* xz = (uint4*)(act + RB_X1 + tile * 14336 + j * 1792) + lane;
#pragma unroll
                for (int i = 0; i < 14; i++) xz[i * 32] = make_uint4(0, 0, 0, 0);
                ((uint4*)(act + RB_ST + (tile * 8 + j) * 128))[lane] = make_uint4(0, 0, 0, 0);
            }
#pragma unroll 1
            for (int ps = 0; ps < 3; ps++) {
                mbar_wait(BAR(B_PUB + 6 + ps), 0);
                wait_flags(g_flag + b * 128 + 64 + lane, target, (0x55u << kh) << (8 * ps));
                warp_arrive(BAR(B_HRDY + ps));
                PROFH(9 + ps);
            }
        } else {
#pragma unroll 1
            for (int k = 0; k < 9; k++) {
                uint32_t* fp = k < 2 ? g_flag + (b + 8 * lane) * 128 + k * 8 + lane : g_flag + (8 * r + lane) * 128 + 16 + k * 8 + j;
                mbar_wait(BAR(B_PUB + k), 0);
                if (k != 4 && k != 5) fence_gpu();
                if (k < 2 ? (lane == 1 || lane == 2) : lane < 8) st_relaxed(fp, target);
                if (k >= 3 && k <= 5) PROFH(k - 3);
            }
        }
    }
}

__global__ void __cluster_dims__(2, 1, 1) __launch_bounds__(384, 1) fused_block_kernel(const __grid_constant__ Params p) {
    extern __shared__ __align__(1024) unsigned char smem[];
    const uint32_t sb = (uint32_t)__cvta_generic_to_shared(smem);
    const int tid = threadIdx.x, lane = tid & 31, warp = __shfl_sync(~0u, tid >> 5, 0);
    const int m = blockIdx.x >> 1;
    int r, nq;
    {
        int g, i;
        if (m < MAP_S) { g = m < 4 ? 15 : 16; i = m & 3; }
        else if (m < MAP_S + 32) { g = (m - MAP_S) & 7; i = (m - MAP_S) >> 3; }
        else if (m < MAP_S + 60) { i = (m - MAP_S - 32) / 7; g = 8 + (m - MAP_S - 32) - 7 * i; }
        else { g = 16; i = m & 3; }
        r = g; nq = i;
    }
    const int j = opaque(2 * nq + (blockIdx.x & 1)), b = 8 * r + j, fs = 4 * kh + nq;
    const uint32_t sc = r == 16;
    if (lane == 0 && warp < 9 && warp != 6 && warp != 7) {
        const int i0 = warp == 8 ? 0 : 8 + 8 * warp, cnt = warp == 0 || warp == 8 ? 1 : warp < 3 ? 2 : 8;
#pragma unroll
        for (int k = 0; k < 8; k++) if (i0 + k != B_WMFULL) mbar_init(BAR(i0 + k), cnt);
        asm volatile("fence.mbarrier_init.release.cluster;" ::: "memory");
        fence_async_smem();
    }

    if (warp >= 8) {
        const int lane = fresh_tid() & 31;
        const bool early = kh == 0, gemv = r < 14;
        const int mcol = early ? 16 * (4 * r + nq) : 2 * DM + 32 * (4 * r + nq);
        const uint32_t wmbuf = sb + OFF_Y + HALF;
        asm volatile("setmaxnreg.dec.sync.aligned.u32 56;");
        if (warp == 9) {
#pragma unroll
            for (int i = 56; i < 64; i++) init_e(BAR(i), 1);
            fence_async_smem();
        }
        if (warp == 8) { init_e(BAR(B_WMFULL), 1); fence_async_smem(); }
        bar_arrive(0, 384);
        asm volatile("barrier.cluster.arrive.relaxed.aligned;" ::: "memory");
        if (warp == 8) {
            if (!sc) {
                expect_e(BAR(B_WMFULL), gemv ? 28672 >> early : 0);
                if (early && gemv) { tma3_e(wmbuf, &p.wm, mcol, 0, 0, BAR(B_WMFULL)); tma3_e(wmbuf + 7168, &p.wm, mcol, 224, 0, BAR(B_WMFULL)); }
#pragma unroll 1
                for (int kb = 0; kb < 7; kb++) {
                    expect_e(BAR(B_XFULL + kb), 16384);
                    tma3_e(sb + OFF_X + kb * 16384, &p.xm, 64 * kb, 128 * r, 0, BAR(B_XFULL + kb));
                }
            }
#pragma unroll 1
            for (int mt = 0; mt < 4; mt++) {
                if (mt == 1) {
                    if (!early && gemv) {
#pragma unroll 1
                        for (int k = 0; k < 4; k++) tma3_e(wmbuf + k * 7168, &p.wm, mcol + (k >> 1) * 16, (k & 1) * 224, 0, BAR(B_WMFULL));
                    }
                    bar_sync(9, 384);
                    if (sc) return;
                    mbar_wait(BAR(B_WMFREE), 0);
                }
                if (mt) mbar_wait(BAR(mt == 1 ? B_MOD1 : mt == 2 ? B_XFREE : B_VRFULL), 0);
                const uint32_t bar = BAR(mt == 3 ? B_WOFULL : B_FULLK + mt), dst = sb + (mt < 2 ? OFF_Y : OFF_X) + (mt & 1) * HALF;
                const int c0 = (mt < 2 ? DM + DM * mt : 0) + 56 * j - 8 * kh;
                if (!sc) {
                    expect_e(bar, HALF);
                    tma3_e(dst, mt == 3 ? &p.wo : &p.qkv, c0, 0, 0, bar);
                    tma3_e(dst + HALF / 2, mt == 3 ? &p.wo : &p.qkv, c0, 224, 0, bar);
                }
            }
        } else {
            if (warp == 10 && !sc) l2_prefetch_e((const char*)p.wqkv + (size_t)b * 9408, 9408);
            bar_sync(9, 384);
            if (sc) return;
            if (warp == 11) {
                const int col = mcol + (early ? lane & 15 : lane);
                const uint32_t tag = (lds1(sb + M_EPOCH) + 1) & 0xFFFFu;
                mbar_wait(BAR(B_GEMV), 0);
                float sum = 0.f;
#pragma unroll
                for (int i = 0; i < 8; i++) sum += *(const float*)(smem + OFF_Y + HALF + 29696 + (i * 32 + col - mcol) * 4);
                sum = bf_round(sum);
                if ((col >= DM && col < 2 * DM) || (col >= 4 * DM && col < 5 * DM)) sum += 1.f;
                uint32_t* mg = g_mod + col + (early ? (lane >> 4) * 4 * 6 * DM : 0);
#pragma unroll 1
                for (int i = gemv ? (early ? 4 : 8) : 0; i > 0; i--, mg += 6 * DM) st_relaxed(mg, (pack2(sum, 0.f) << 16) | tag);
                warp_arrive(BAR(B_WMFREE));
            }
        }
    }
    if (LIKELY(warp < 8)) {
        const int w = warp >> 2, wi = warp & 3;
#define COORDS const int t = fresh_tid() & 127, lane = t & 31, q = lane & 3, lr = lane >> 2, ra = 64 * w + 16 * wi + lr; \
        const uint32_t lx = (lane >> 4) ^ (lane & 7), mrow = (64 * w + 16 * wi + ((lane >> 3) & 1) * 8 + (lane & 7)) * 128; \
        (void)q; (void)lr; (void)ra; (void)lx; (void)mrow;
        const int sid = 2 * (j & 3) + w;
#define RUN(k) (!sc || sid == (k))
#define WAIT(i, par) mbar_wait_c(BAR(i), (par) | sc)
        constexpr uint64_t DB128 = dconst(4096, 1024, 1);
        {
            const int wd = fresh_tid();
            const uint32_t cb = wd < 224 ? __ldg((const uint32_t*)p.c + wd) : 0u;
            if (wd == 255 && !sc) sts1(sb + M_EPOCH, atomicAdd(&g_ticket, 1u) / NCTA);
            sts1(sb + OFF_Y + HALF + 28672 + (wd >> 3) * 32 + (wd & 3) * 8 + (wd & 4), pack2(silu_bf(cb & 0xFFFFu), silu_bf(cb >> 16)));
        }
        bar_arrive(9, 384);
        bar_sync(0, 384);
        asm volatile("barrier.cluster.arrive.relaxed.aligned;" ::: "memory");
        asm volatile("setmaxnreg.inc.sync.aligned.u32 224;");
        PROFC(0);
        uint32_t xr[16];
        {
            COORDS
            uint32_t h[112];
            if (RUN(0)) {
                float ds[4] = {}, da[2][4] = {}, db[2][4] = {};
                const uint32_t ONE2 = 0x3F803F80u;
                if (kh == 0) { WAIT(B_WMFULL, 0); gemv_part(sb + OFF_Y + HALF, 1, warp, lane); warp_arrive(BAR(B_GEMV)); }
#pragma unroll
                for (int kb = 0; kb < 7; kb++) {
                    WAIT(B_XFULL + kb, 0);
#pragma unroll
                    for (int k4 = 0; k4 < 4; k4++) ldsm4(sb + OFF_X + mrow + kb * 16384 + (((2 * k4) ^ lx) << 4), h + 16 * kb + 4 * k4);
#pragma unroll
                    for (int k4 = 0; k4 < 4; k4++) {
                        const uint32_t* f = h + 16 * kb + 4 * k4;
                        mma16816(ds, f[0], f[1], f[2], f[3], ONE2, ONE2);
                        mma1688(da[0], f[0], f[1], f[0]); mma1688(db[0], f[0], f[1], f[1]);
                        mma1688(da[1], f[2], f[3], f[2]); mma1688(db[1], f[2], f[3], f[3]);
                    }
                }
#pragma unroll
                for (int i = 0; i < 4; i++) {
                    const int ch = 7 * j + 2 * i + (lane >> 4);
                    ldsm4(sb + OFF_X + mrow + (ch >> 3) * 16384 + (((ch ^ lane) & 7) << 4), xr + 4 * i);
                }
                warp_arrive(BAR(B_XFREE));
                float qa = (lr & 1) ? da[0][1] + da[1][1] : da[0][0] + da[1][0];
                float qb = (lr & 1) ? db[0][3] + db[1][3] : db[0][2] + db[1][2];
                const int src = (lane & ~3) | (lr >> 1);
                qa = __shfl_sync(~0u, qa, src);
                qb = __shfl_sync(~0u, qb, src);
                uint32_t ra2, na2, rb2, nb2;
                ln_coeffs(ds[0] * (1.f / DM), qa * (1.f / DM), ra2, na2);
                ln_coeffs(ds[2] * (1.f / DM), qb * (1.f / DM), rb2, nb2);
#pragma unroll
                for (int i = 0; i < 112; i += 2) { h[i] = hfma2(h[i], ra2, na2); h[i + 1] = hfma2(h[i + 1], rb2, nb2); }
                if (kh == 1) { WAIT(B_WMFULL, 0); gemv_part(sb + OFF_Y + HALF, 2, warp, lane); warp_arrive(BAR(B_GEMV)); }
            } else { reg_def<112>(h); reg_def<16>(xr); }
            PROFC(1);
            if (RUN(1)) {
                float ak[28], av[28], aq[28];
                uint32_t kp[14], vp[14];
                const uint64_t bq0 = (DB128 & ~0xFFFFFFFFull) | (mkdesc(sb + OFF_X, DB128) + kh), bk0 = bq0 + (OFF_Y >> 4), bv0 = bk0 + (HALF >> 4);
                uint32_t* kvg = act + RB_KV + j * 7168 + (8 * w + 2 * wi) * 224 + lane;
                {
                    const int i = min(fresh_tid(), 223);
                    const uint4* src = mod_src(i, r, j, false);
                    mod_store(sb, ld_relaxed4(src), src, i, sc);
                    if (!sc) bar_sync(3, 256);
                    if (warp == 0) warp_arrive(BAR(B_MOD1));
                }
                WAIT(B_FULLK, 0);
                PROFC(2);
                reg_def<28>(ak);
#pragma unroll
                for (int g4 = 0; g4 < 4; g4++) {
#pragma unroll
                    for (int ks = 7 * g4; ks < 7 * g4 + 7; ks++) {
                        const uint4 st = *(const uint4*)(smem + M_ST + ks * 64 + q * 16);
                        h[4 * ks] = hfma2(h[4 * ks], st.x, st.y); h[4 * ks + 1] = hfma2(h[4 * ks + 1], st.x, st.y);
                        h[4 * ks + 2] = hfma2(h[4 * ks + 2], st.z, st.w); h[4 * ks + 3] = hfma2(h[4 * ks + 3], st.z, st.w);
                    }
                    WG_FENCE();
#pragma unroll
                    for (int ks = 7 * g4; ks < 7 * g4 + 7; ks++) wgmma_rl_56(ak, h[4 * ks], h[4 * ks + 1], h[4 * ks + 2], h[4 * ks + 3], bk0 + ks * 128, ks != 0);
                }
                WG_COMMIT();
                PROFC(3);
                WAIT(B_FULLV, 0);
                reg_def<28>(av);
                WG_FENCE();
#pragma unroll
                for (int ks = 0; ks < 8; ks++) wgmma_rl_56(av, h[4 * ks], h[4 * ks + 1], h[4 * ks + 2], h[4 * ks + 3], bv0 + ks * 128, ks != 0);
                WG_COMMIT();
                WG_WAIT(1);
                reg_fence<28>(ak);
#pragma unroll
                for (int g = 0; g < 7; g++) {
                    kp[2 * g] = pack2(ak[4 * g], ak[4 * g + 1]); kp[2 * g + 1] = pack2(ak[4 * g + 2], ak[4 * g + 3]);
                    kvg[g * 32] = kp[2 * g]; kvg[224 + g * 32] = kp[2 * g + 1];
                }
                warp_arrive(BAR(B_PUB));
                PROFC(4);
                WG_FENCE();
#pragma unroll
                for (int ks = 8; ks < 28; ks++) wgmma_rl_56(av, h[4 * ks], h[4 * ks + 1], h[4 * ks + 2], h[4 * ks + 3], bv0 + ks * 128, 1);
                WG_COMMIT();
                WAIT(B_FULLQ, 0);
                reg_def<28>(aq);
                WG_FENCE();
#pragma unroll
                for (int ks = 0; ks < 8; ks++) wgmma_rl_56(aq, h[4 * ks], h[4 * ks + 1], h[4 * ks + 2], h[4 * ks + 3], bq0 + ks * 128, ks != 0);
                WG_COMMIT();
                WG_WAIT(1);
                reg_fence<28>(av);
#pragma unroll
                for (int g = 0; g < 7; g++) {
                    vp[2 * g] = pack2(av[4 * g], av[4 * g + 1]); vp[2 * g + 1] = pack2(av[4 * g + 2], av[4 * g + 3]);
                    kvg[3584 + g * 32] = vp[2 * g]; kvg[3584 + 224 + g * 32] = vp[2 * g + 1];
                }
                warp_arrive(BAR(B_PUB + 1));
                const uint4* msrc = mod_src(128 * w + t, r, j, true);
                const uint4 mv = ld_relaxed4(msrc);
                PROFC(5);
                WG_FENCE();
#pragma unroll
                for (int ks = 8; ks < 28; ks++) wgmma_rl_56(aq, h[4 * ks], h[4 * ks + 1], h[4 * ks + 2], h[4 * ks + 3], bq0 + ks * 128, 1);
                WG_COMMIT();
                WAIT(B_PUB + 1, 0);
                mod_store(sb, mv, msrc, 128 * w + t, sc);
                const uint32_t rg = 8 * w + 2 * wi + ((lane >> 3) & 1);
                const uint32_t ko = sb + OFF_Y + Y_KOWN + rg * 896 + (lane & 7) * 16, qo = sb + OFF_Y + Y_Q + rg * 1024 + (lane >> 4) * 128 + (lane & 7) * 16;
#pragma unroll
                for (int g = 0; g < 6; g += 2) {
                    stsm4(ko + (g + (lane >> 4)) * 128, kp[2 * g], kp[2 * g + 1], kp[2 * g + 2], kp[2 * g + 3]);
                    stsm4(ko + (Y_VOWN - Y_KOWN) + (g + (lane >> 4)) * 128, vp[2 * g], vp[2 * g + 1], vp[2 * g + 2], vp[2 * g + 3]);
                }
                stsm4(ko + (lane >> 4) * (Y_VOWN - Y_KOWN) + 6 * 128, kp[12], kp[13], vp[12], vp[13]);
                WG_WAIT(0);
                reg_fence<28>(aq);
                __syncwarp();
                if (lane < 3 && w == 1) mbar_arrive(BAR(B_EMPTY + lane));
                uint32_t qp[14];
#pragma unroll
                for (int i = 0; i < 14; i++) qp[i] = pack2(aq[2 * i], aq[2 * i + 1]);
                stsm4(qo, qp[0], qp[1], qp[2], qp[3]);
                stsm4(qo + 256, qp[4], qp[5], q < 2 ? qp[6] : 0u, q < 2 ? qp[7] : 0u);
                stsm4(qo + 512, q < 2 ? 0u : qp[6], q < 2 ? 0u : qp[7], qp[8], qp[9]);
                stsm4(qo + 768, qp[10], qp[11], qp[12], qp[13]);
                if (!sc) bar_sync(3, 256);
            }
        }
        PROFC(6);
        WAIT(B_KRFULL, 0);
        PROFC(7);
        if (RUN(2)) {
#pragma unroll 1
            for (int hf = sc; hf < 2; hf++) {
                COORDS
                float s[136];
                float na = 0.f, nb = 0.f;
                const float CS = 0.18898223650461361f * 1.4426950408889634f;
                const int kg0 = 8 * hf + 2 * wi;
                const int pmin = 16 - 8 * r - 4 * hf - wi;
                const float NEG = __int_as_float(0xFF800000);
                {
                    uint32_t F[8];
                    const uint32_t qa = sb + OFF_Y + Y_Q + (kg0 + ((lane >> 3) & 1)) * 1024 + (4 * w + (lane >> 4)) * 128 + (lane & 7) * 16;
                    ldsm4(qa, F); ldsm4(qa + 256, F + 4);
                    uint32_t ka = sb + OFF_Y + Y_K + kg0 * 896 + (3 * w + (lane >> 3)) * 128 + (lane & 7) * 16;
#pragma unroll
                    for (int g = 0; g < 34; g++) {
                        uint32_t B[4];
                        if (g >= 12 && g % 4 == 0) ka += __float_as_uint(s[4 * (g - 12)]) & p.zero;
                        ldsm4(ka + g * 896, B);
                        mma16816_first(s + 4 * g, F[0], F[1], F[2], F[3], B[0], B[1]);
                        mma16816_v(s + 4 * g, F[4], F[5], F[6], F[7], B[2], B[3]);
                    }
                    const bool c0 = 2 * q > lr, c1 = 2 * q + 1 > lr;
                    if (!c0) { s[0] = NEG; s[6] = NEG; }
                    if (!c1) { s[1] = NEG; s[7] = NEG; }
                    s[2] = NEG; s[3] = NEG;
                    if (c0) { s[128] = NEG; s[134] = NEG; }
                    if (c1) { s[129] = NEG; s[135] = NEG; }
                    s[132] = NEG; s[133] = NEG;
                    float ma = NEG, mb = NEG;
#pragma unroll
                    for (int pp = 0; pp < 17; pp++) {
                        const float* e = s + 8 * pp;
                        const float bias = pp < pmin ? NEG : 0.f;
                        ma = fmaxf(ma, fmaxf(fmaxf(e[0], e[1]), fmaxf(e[4], e[5])) + bias);
                        mb = fmaxf(mb, fmaxf(fmaxf(e[2], e[3]), fmaxf(e[6], e[7])) + bias);
                    }
                    ma = fmaxf(ma, __shfl_xor_sync(~0u, ma, 1)); mb = fmaxf(mb, __shfl_xor_sync(~0u, mb, 1));
                    ma = fmaxf(ma, __shfl_xor_sync(~0u, ma, 2)); mb = fmaxf(mb, __shfl_xor_sync(~0u, mb, 2));
                    na = -ma * CS; nb = -mb * CS;
                }
                PROFC(8 + 3 * hf);
                {
                    WAIT(B_VRFULL, 0);
                    float o[16] = {}, rs[4] = {};
                    uint32_t pk[2];
                    const uint32_t va = sb + OFF_Y + Y_VR + (kg0 + ((lane >> 3) & 1)) * 896 + (3 * w + (lane >> 4)) * 128 + (lane & 7) * 16;
#pragma unroll
                    for (int pp = 0; pp < 17; pp++) {
                        uint32_t B[8];
                        const uint32_t v = va + pp * 1792 + (pp == 16 || (pp >= 9 && kg0 + 2 * pp >= 32) ? Y_VOWN - 32 * 896 : 0);
                        ldsm4t(v, B); ldsm4t(v + 256, B + 4);
                        float e[8];
                        const float bias = __uint_as_float((pp < pmin ? 0xFF800000u : 0u) | ((pp < 2 ? B[0] : pk[pp & 1]) & p.zero));
#pragma unroll
                        for (int i = 0; i < 8; i++) e[i] = ex2(fmaf(s[8 * pp + i], CS, ((i & 2) ? nb : na) + bias));
                        const uint32_t p0 = pack2(e[0], e[1]), p1 = pack2(e[2], e[3]), p2 = pack2(e[4], e[5]), p3 = pack2(e[6], e[7]);
                        pk[pp & 1] = p3;
                        mma16816(rs, p0, p1, p2, p3, 0x3F803F80u, 0x3F803F80u);
#pragma unroll
                        for (int g = 0; g < 4; g++) mma16816(o + 4 * g, p0, p1, p2, p3, B[2 * g], B[2 * g + 1]);
                    }
                    PROFC(9 + 3 * hf);
                    const float ia = rcp(rs[0]), ib = rcp(rs[2]);
                    uint32_t* og = act + RB_O + hf * 14336 + (7 * j + 3 * w) * 256 + wi * 64 + lane;
#pragma unroll
                    for (int g = 0; g < 4; g++) {
                        if ((g == 3 - 3 * w) ? ((q >> 1) == w) : true) {
                            og[g * 256] = pack2(o[4 * g] * ia, o[4 * g + 1] * ia);
                            og[g * 256 + 32] = pack2(o[4 * g + 2] * ib, o[4 * g + 3] * ib);
                        }
                    }
                    warp_arrive(BAR(B_PUB + 2 + hf));
                    PROFC(10 + 3 * hf);
                }
            }
        }
        uint32_t x1p[14];
        COORDS
        constexpr uint64_t DT = dconst(1024, 128, 0);
        const int tile = opaque((lds1(sb + M_EPOCH) & 1) * 2 + w);
        if (RUN(4)) {
            float ac[28];
            const uint32_t ad = mkdesc(sb + (w ? OFF_Y + HALF : OFF_X), DT), bd = mkdesc(sb + OFF_X + HALF, DB128) + kh;
            WAIT(B_WOFULL, 0);
            WAIT(B_GFULL + w, 0);
            PROFC(28);
            reg_def<28>(ac);
#pragma unroll 1
            for (int u = 0; u < 4; u++) {
                if (u == 2) WAIT(B_XFULL + 2 + w, 1);
                WG_FENCE();
#pragma unroll
                for (int i = 0; i < 7; i++) wgmma_ss_56<DT, DB128>(ac, ad + (7 * u + i) * 128, bd + (7 * u + i) * 128, (u | i) != 0);
            }
            WG_COMMIT();
            WG_WAIT(0);
            reg_fence<28>(ac);
            PROFC(14);
            __syncwarp();
            if (lane < 3) mbar_arrive(BAR(B_EMPTY + 4 - w + lane));
            if (lane < 3 && w == 0) mbar_arrive(BAR(B_EMPTY + lane));
            float ds[4] = {}, da[4] = {}, db[4] = {};
            uint32_t* xo = act + RB_X1 + tile * 14336 + 7 * j * 256 + wi * 64 + lane;
#pragma unroll
            for (int g = 0; g < 7; g++) {
                const float2 ga = *(const float2*)(smem + M_G + (8 * g + 2 * q) * 4);
                x1p[2 * g] = pack2(fmaf(ga.x, ac[4 * g], bf_lo(xr[2 * g])), fmaf(ga.y, ac[4 * g + 1], bf_hi(xr[2 * g])));
                x1p[2 * g + 1] = pack2(fmaf(ga.x, ac[4 * g + 2], bf_lo(xr[2 * g + 1])), fmaf(ga.y, ac[4 * g + 3], bf_hi(xr[2 * g + 1])));
                st_relaxed(xo + g * 256, nz(x1p[2 * g])); st_relaxed(xo + g * 256 + 32, nz(x1p[2 * g + 1]));
                mma1688(ds, x1p[2 * g], x1p[2 * g + 1], 0x3F803F80u);
                mma1688(da, x1p[2 * g], x1p[2 * g + 1], x1p[2 * g]);
                mma1688(db, x1p[2 * g], x1p[2 * g + 1], x1p[2 * g + 1]);
            }
            const int src = (lane & ~3) | (lr >> 1);
            const float qa = __shfl_sync(~0u, (lr & 1) ? da[1] : da[0], src), qb = __shfl_sync(~0u, (lr & 1) ? db[3] : db[2], src);
            const float kk = (q & 1) ? ((q & 2) ? qb : qa) : ((q & 2) ? ds[2] : ds[0]);
            st_relaxed(act + RB_ST + ((tile * 8 + j) * 64 + 16 * wi + lr + 4 * (q & 2)) * 2 + (q & 1), nz(__float_as_uint(kk)));
            __syncwarp();
            if (lane < 2) mbar_arrive(BAR(B_PUB + 4 + w));
        } else reg_def<14>(x1p);
        PROFC(15);
        uint32_t h2a[32], h2b[24];
        {
            const int fa = pass_f(fs, 0), fb = pass_f(fs, 1), fc = pass_f(fs, 2);
            uint32_t* h2g = act + RB_H2 + (8 * w + 2 * wi) * 32 + lane;
            const uint32_t a0 = mkdesc(sb + OFF_Y + w * HALF, DT);
            if (RUN(3)) {
                uint32_t ra2, na2, rb2, nb2;
                {
                    const uint32_t* sg = act + RB_ST + ((tile * 8 + 2 * q) * 64 + 16 * wi + lr) * 2;
                    uint2 u[4];
                    WAIT(B_GFULL + 2 + w, 0);
                    PROFC(16);
#pragma unroll
                    for (int i = 0; i < 4; i++) { const float2 v = lds2f(sb + OFF_X + X_STAT + w * 49152 + ((2 * q + (i >> 1)) * 64 + 16 * wi + lr + 8 * (i & 1)) * 8); u[i] = make_uint2(__float_as_uint(v.x), __float_as_uint(v.y)); }
                    while (__any_sync(~0u, min(min(min(u[0].x, u[0].y), min(u[1].x, u[1].y)), min(min(u[2].x, u[2].y), min(u[3].x, u[3].y))) < 1u - sc)) {
#pragma unroll
                        for (int i = 0; i < 4; i++) u[i] = ld_relaxed2(sg + (i >> 1) * 128 + (i & 1) * 16);
                    }
                    warp_arrive(BAR(B_EMPTY + 3 + 3 * w));
                    float v[4] = {__uint_as_float(u[0].x) + __uint_as_float(u[2].x), __uint_as_float(u[0].y) + __uint_as_float(u[2].y),
                                  __uint_as_float(u[1].x) + __uint_as_float(u[3].x), __uint_as_float(u[1].y) + __uint_as_float(u[3].y)};
#pragma unroll
                    for (int i = 0; i < 4; i++) { v[i] += __shfl_xor_sync(~0u, v[i], 1); v[i] += __shfl_xor_sync(~0u, v[i], 2); }
                    ln_coeffs(v[0] * (1.f / DM), v[1] * (1.f / DM), ra2, na2);
                    ln_coeffs(v[2] * (1.f / DM), v[3] * (1.f / DM), rb2, nb2);
                }
                const uint32_t ha = sb + OFF_Y + w * HALF + (lane >> 4) * 1024 + (2 * wi + ((lane >> 3) & 1)) * 128 + (lane & 7) * 16;
                const uint32_t sta = sb + M_ST + q * 16;
                const uint32_t* xg = act + RB_X1 + tile * 14336 + (lane >> 4) * 256 + wi * 64 + (lane & 15) * 4;
                uint32_t x[8];
                const uint32_t xs = sb + OFF_Y + w * HALF + (lane >> 4) * 1024 + wi * 256 + (lane & 15) * 16;
                uint4 st[2];
                auto load = [&](int s) {
                    if (s == 4) mbar_wait_c(BAR(B_XFULL + 4 + w), 1);
                    ldsm4(ha + s * 4096, x); ldsm4(ha + s * 4096 + 2048, x + 4);
                    st[0] = lds4(sta + s * 128); st[1] = lds4(sta + s * 128 + 64);
                };
                auto prep = [&](int s, uint32_t* f) {
                    if (__any_sync(~0u, min(min(min(x[0], x[1]), min(x[2], x[3])), min(min(x[4], x[5]), min(x[6], x[7]))) < 1u - sc)) {
                        WG_WAIT(0);
                        x1_fix(xg, xs, s);
                        ldsm4(ha + s * 4096, x); ldsm4(ha + s * 4096 + 2048, x + 4);
                    }
#pragma unroll
                    for (int i = 0; i < 2; i++) {
                        f[4 * i] = hfma2(hfma2(x[4 * i], ra2, na2), st[i].x, st[i].y); f[4 * i + 1] = hfma2(hfma2(x[4 * i + 1], rb2, nb2), st[i].x, st[i].y);
                        f[4 * i + 2] = hfma2(hfma2(x[4 * i + 2], ra2, na2), st[i].z, st[i].w); f[4 * i + 3] = hfma2(hfma2(x[4 * i + 3], rb2, nb2), st[i].z, st[i].w);
                    }
                    if (s < 13) load(s + 1);
                    stsm4(ha + s * 4096, f[0], f[1], f[2], f[3]); stsm4(ha + s * 4096 + 2048, f[4], f[5], f[6], f[7]);
                };
                float ac[128];
                uint32_t fr[3][8];
                const uint32_t bx = mkdesc(sb, DB128);
                reg_def<128>(ac);
                load(0);
                prep(0, fr[0]);
                PROFC(17);
#pragma unroll
                for (int s = 0; s < 14; s++) {
                    const uint32_t* f = fr[s % 3];
                    const uint32_t bd = bx + g1_slot(s) * 1024;
                    WAIT(B_FULL + g1_slot(s), s >= 7);
                    WG_FENCE();
                    wgmma_rs_256<DB128>(ac, f[0], f[1], f[2], f[3], bd, s != 0);
                    wgmma_rs_256<DB128>(ac, f[4], f[5], f[6], f[7], bd + 128, 1);
                    WG_COMMIT();
                    if (s < 13) prep(s + 1, fr[(s + 1) % 3]);
                    if (s > 0) { WG_WAIT(1); warp_arrive(BAR(B_EMPTY + g1_slot(s - 1))); }
                }
                fence_async_smem();
                PROFC(18);
                WG_WAIT(0);
                reg_fence<128>(ac);
                warp_arrive(BAR(B_EMPTY + 6));
#pragma unroll
                for (int g = 0; g < 16; g++) {
                    h2a[2 * g] = hmul2(pack2_relu(ac[4 * g], ac[4 * g + 1]), pack2(ac[64 + 4 * g], ac[64 + 4 * g + 1]));
                    h2a[2 * g + 1] = hmul2(pack2_relu(ac[4 * g + 2], ac[4 * g + 3]), pack2(ac[64 + 4 * g + 2], ac[64 + 4 * g + 3]));
                }
                bar_sync(1 + w, 128);
            } else reg_def<32>(h2a);
            PROFC(19);
            if (RUN(5)) {
                float ac[64];
                reg_def<64>(ac);
                const uint32_t bx = mkdesc(sb, dconst(8192, 1024, 1));
#pragma unroll kB
                for (int s = 0; s < 7; s++) {
                    WAIT(B_FULL + s, 0);
                    const uint32_t ad = a0 + s * 512, bd = bx + (slot_off(s) >> 4);
                    WG_FENCE();
#pragma unroll
                    for (int k = 0; k < 4; k++) wgmma_ss_128<DT, DB128>(ac, ad + k * 128, bd + k * 128, (s | k) != 0);
                    WG_COMMIT();
                    if (s == 1) {
#pragma unroll
                        for (int g = 0; g < 16; g++) { h2g[(fa / 8 + g) * 512] = h2a[2 * g]; h2g[(fa / 8 + g) * 512 + 32] = h2a[2 * g + 1]; }
                        warp_arrive(BAR(B_PUB + 6));
                    }
                    if (s > 0) { WG_WAIT(1); warp_arrive(BAR(B_EMPTY + s - 1)); }
                }
                WG_WAIT(0);
                reg_fence<64>(ac);
                warp_arrive(BAR(B_EMPTY + 6));
#pragma unroll
                for (int g = 0; g < 8; g++) {
                    h2b[2 * g] = hmul2(pack2_relu(ac[4 * g], ac[4 * g + 1]), pack2(ac[32 + 4 * g], ac[32 + 4 * g + 1]));
                    h2b[2 * g + 1] = hmul2(pack2_relu(ac[4 * g + 2], ac[4 * g + 3]), pack2(ac[32 + 4 * g + 2], ac[32 + 4 * g + 3]));
                }
            } else reg_def<16>(h2b);
            PROFC(27);
            if (RUN(6)) {
                float ac[32];
                reg_def<32>(ac);
                const uint32_t bx = mkdesc(sb, dconst(4096, 512, 2));
#pragma unroll kC
                for (int s = 0; s < 7; s++) {
                    WAIT(B_FULL + s, 1);
                    const uint32_t ad = a0 + s * 512, bd = bx + (slot_off(s) >> 4);
                    WG_FENCE();
#pragma unroll
                    for (int k = 0; k < 4; k++) wgmma_ss_64<DT, dconst(4096, 512, 2)>(ac, ad + k * 128, bd + k * 64, (s | k) != 0);
                    WG_COMMIT();
                    if (s == 1) {
#pragma unroll
                        for (int g = 0; g < 8; g++) { h2g[(fb / 8 + g) * 512] = h2b[2 * g]; h2g[(fb / 8 + g) * 512 + 32] = h2b[2 * g + 1]; }
                        warp_arrive(BAR(B_PUB + 7));
                    }
                    if (s > 0) { WG_WAIT(1); warp_arrive(BAR(B_EMPTY + s - 1)); }
                }
                WG_WAIT(0);
                reg_fence<32>(ac);
                __syncwarp();
                if (lane < 6) mbar_arrive(BAR(B_EMPTY + 6 + lane));
                PROFC(20);
#pragma unroll
                for (int g = 0; g < 4; g++) {
                    h2b[16 + 2 * g] = hmul2(pack2_relu(ac[4 * g], ac[4 * g + 1]), pack2(ac[16 + 4 * g], ac[16 + 4 * g + 1]));
                    h2b[16 + 2 * g + 1] = hmul2(pack2_relu(ac[4 * g + 2], ac[4 * g + 3]), pack2(ac[16 + 4 * g + 2], ac[16 + 4 * g + 3]));
                    h2g[(fc / 8 + g) * 512] = h2b[16 + 2 * g]; h2g[(fc / 8 + g) * 512 + 32] = h2b[16 + 2 * g + 1];
                }
                warp_arrive(BAR(B_PUB + 8));
                asm volatile("barrier.cluster.wait.aligned;" ::: "memory");
                if (lane == 0 && !sc) {
                    uint32_t rb;
                    asm volatile("mapa.shared::cluster.u32 %0, %1, %2;" : "=r"(rb) : "r"(BAR(B_PEER)), "r"(kh ^ 1));
                    asm volatile("mbarrier.arrive.relaxed.cluster.shared::cluster.b64 _, [%0];" ::"r"(rb) : "memory");
                }
            } else reg_def<8>(h2b + 16);
        }
        PROFC(21);
        if (RUN(7)) {
            float ac[56];
            reg_def<56>(ac);
            constexpr uint64_t DAN = dconst(2048, 128, 0);
            constexpr uint64_t DW = dconst(128, 512, 0);
            const uint32_t bx = mkdesc(sb, DW);
#pragma unroll
            for (int e = 0; e < 4; e++) {
                WAIT(B_FULL + e, 0);
                const uint32_t bd = bx + (slot_off(e) >> 4);
                const uint32_t* hh = e < 2 ? h2a + 16 * e : h2b + 16 * (e - 2);
                WG_FENCE();
#pragma unroll
                for (int k = 0; k < (e < 3 ? 4 : 2); k++) wgmma_rs_112<DW>(ac, hh[4 * k], hh[4 * k + 1], hh[4 * k + 2], hh[4 * k + 3], bd + (k >> 1) * 512 + (k & 1) * 16, (e | k) != 0);
                WG_COMMIT();
                if (e > 0) { WG_WAIT(1); warp_arrive(BAR(B_EMPTY + e - 1)); }
            }
            PROFC(22);
            uint32_t ad = mkdesc(sb + 4 * 16384 + 8192 + w * 1024, DAN), bd = bx + 4 * 1024, fb_ = BAR(B_FULL + 4), eb_ = BAR(B_EMPTY + 3), par = sc;
#pragma unroll 1
            for (int e = 4; e < 25; e++) {
                mbar_wait_c(fb_, par);
                WG_FENCE();
                wgmma_ss_112<DAN, DW>(ac, ad, bd, 1);
                wgmma_ss_112<DAN, DW>(ac, ad + 256, bd + 16, 1);
                WG_COMMIT();
                WG_WAIT(1);
                warp_arrive(eb_);
                eb_ = fb_ + 8 * (B_EMPTY - B_FULL);
                ad += 1024; bd += 1024; fb_ += 8;
                if (e == 11 || e == 23) { ad -= 12 * 1024; bd -= 12 * 1024; fb_ -= 96; par = (par ^ 1) | sc; }
            }
            mbar_wait_cluster(BAR(B_PEER), sc);
            WG_WAIT(0);
            reg_fence<56>(ac);
            PROFC(24);
            uint32_t rdst, rbar;
            asm volatile("mapa.shared::cluster.u32 %0, %1, %2;" : "=r"(rdst) : "r"(sb + OFF_Y + (5 + w) * 16384 + t * 16), "r"(kh ^ 1 ^ sc));
            asm volatile("mapa.shared::cluster.u32 %0, %1, %2;" : "=r"(rbar) : "r"(BAR(B_XCH + w)), "r"(kh ^ 1 ^ sc));
#pragma unroll
            for (int g = 0; g < 7; g++) {
                const float v0 = ac[28 + 4 * g + 0], v1 = ac[28 + 4 * g + 1];
                const float v2 = ac[28 + 4 * g + 2], v3 = ac[28 + 4 * g + 3];
                if (!sc) asm volatile("st.async.shared::cluster.mbarrier::complete_tx::bytes.v4.f32 [%0], {%1,%2,%3,%4}, [%5];"
                             ::"r"(rdst + g * 2048), "f"(v0), "f"(v1), "f"(v2), "f"(v3), "r"(rbar) : "memory");
            }
            mbar_wait_cluster(BAR(B_XCH + w), sc);
            PROFC(25);
            bf16* og = (sc ? (bf16*)act : p.out + (size_t)128 * r * DM) + (size_t)ra * DM + 56 * j + 2 * q;
#pragma unroll
            for (int g = 0; g < 7; g++) {
                const uint4 rv = *(const uint4*)(smem + OFF_Y + (5 + w) * 16384 + t * 16 + g * 2048);
                const float2 gb = *(const float2*)(smem + M_G + 224 + (8 * g + 2 * q) * 4);
                const float v0 = ac[4 * g + 0] + __uint_as_float(rv.x), v1 = ac[4 * g + 1] + __uint_as_float(rv.y);
                const float v2 = ac[4 * g + 2] + __uint_as_float(rv.z), v3 = ac[4 * g + 3] + __uint_as_float(rv.w);
                *(uint32_t*)(og + 8 * g) = pack2(fmaf(gb.x, v0, bf_lo(x1p[2 * g])), fmaf(gb.y, v1, bf_hi(x1p[2 * g])));
                *(uint32_t*)(og + 8 * DM + 8 * g) = pack2(fmaf(gb.x, v2, bf_lo(x1p[2 * g + 1])), fmaf(gb.y, v3, bf_hi(x1p[2 * g + 1])));
            }
        }
        PROFC(26);
        bar_sync(1 + w, 128);
        if (wi == 0) warp_arrive(BAR(B_DONE));
        return;
    }
    helper_late(p, r, j, warp PROF_ARGS);
}

#undef act
typedef CUresult (*EncodeFn)(CUtensorMap*, CUtensorMapDataType, cuuint32_t, void*, const cuuint64_t*, const cuuint64_t*, const cuuint32_t*,
                             const cuuint32_t*, CUtensorMapInterleave, CUtensorMapSwizzle, CUtensorMapL2promotion, CUtensorMapFloatOOBfill);

static void make_map(EncodeFn fn, CUtensorMap* m, const void* ptr, uint64_t d0, uint64_t d1, uint64_t d2, uint64_t s1, uint64_t s2,
                     uint32_t b0, uint32_t b1, uint32_t b2, CUtensorMapSwizzle sw) {
    cuuint64_t dims[3] = {d0, d1, d2}, strides[2] = {s1, s2};
    cuuint32_t box[3] = {b0, b1, b2}, es[3] = {1, 1, 1};
    CUresult rc = fn(m, CU_TENSOR_MAP_DATA_TYPE_BFLOAT16, 3, (void*)ptr, dims, strides, box, es, CU_TENSOR_MAP_INTERLEAVE_NONE, sw,
                     CU_TENSOR_MAP_L2_PROMOTION_L2_128B, CU_TENSOR_MAP_FLOAT_OOB_FILL_NONE);
    (void)rc;
}

extern "C" void kernel_launch(void* const* d_in, const int* in_sizes, int n_in, void* d_out, int out_size) {
    (void)in_sizes; (void)n_in; (void)out_size;
    static EncodeFn fn = nullptr;
    static uint32_t* act_base = nullptr;
    if (!fn) {
        cudaDriverEntryPointQueryResult st;
        cudaGetDriverEntryPoint("cuTensorMapEncodeTiled", (void**)&fn, cudaEnableDefault, &st);
        void* a = nullptr;
        cudaGetSymbolAddress(&a, g_act);
        act_base = (uint32_t*)(((uintptr_t)a + 0xFFFFF) & ~(uintptr_t)0xFFFFF);
        cudaFuncSetAttribute(fused_block_kernel, cudaFuncAttributeMaxDynamicSharedMemorySize, SMEM_BYTES);
    }
    Params p;
    p.x = (const bf16*)d_in[0];
    const bf16* wqkv = (const bf16*)d_in[1];
    p.wqkv = wqkv;
    p.wop = (const bf16*)d_in[2];
    p.wg = (const bf16*)d_in[4];
    p.wu = (const bf16*)d_in[5];
    p.wd = (const bf16*)d_in[6];
    p.c = (const bf16*)d_in[7];
    p.wmod = (const bf16*)d_in[8];
    p.out = (bf16*)d_out;
    p.zero = 0;
    p.actb = act_base;
    make_map(fn, &p.wm, p.wmod, 2688, 448, 1, 5376, 5376 * 448, 16, 224, 1, CU_TENSOR_MAP_SWIZZLE_NONE);
    make_map(fn, &p.xm, p.x, 448, 2048, 1, 896, 896 * 2048, 64, 128, 1, CU_TENSOR_MAP_SWIZZLE_128B);
    make_map(fn, &p.qkv, wqkv, 1344, 448, 1, 2688, 2688 * 448, 64, 224, 1, CU_TENSOR_MAP_SWIZZLE_128B);
    make_map(fn, &p.wo, p.wop, 448, 448, 1, 896, 896 * 448, 64, 224, 1, CU_TENSOR_MAP_SWIZZLE_128B);
    make_map(fn, &p.ga, p.wg, 64, 448, 28, 3584, 128, 64, 32, 2, CU_TENSOR_MAP_SWIZZLE_128B);
    make_map(fn, &p.ua, p.wu, 64, 448, 28, 3584, 128, 64, 32, 2, CU_TENSOR_MAP_SWIZZLE_128B);
    make_map(fn, &p.gb, p.wg, 64, 448, 28, 3584, 128, 64, 64, 1, CU_TENSOR_MAP_SWIZZLE_128B);
    make_map(fn, &p.ub, p.wu, 64, 448, 28, 3584, 128, 64, 64, 1, CU_TENSOR_MAP_SWIZZLE_128B);
    make_map(fn, &p.gc, p.wg, 32, 448, 56, 3584, 64, 32, 64, 1, CU_TENSOR_MAP_SWIZZLE_64B);
    make_map(fn, &p.uc, p.wu, 32, 448, 56, 3584, 64, 32, 64, 1, CU_TENSOR_MAP_SWIZZLE_64B);
    make_map(fn, &p.dn, p.wd, 8, 1792, 56, 896, 16, 8, 32, 7, CU_TENSOR_MAP_SWIZZLE_NONE);
    fused_block_kernel<<<GRID, 384, SMEM_BYTES>>>(p);
}
```

```cpp
#include <cuda_runtime.h>
#include <cuda_bf16.h>
#include <cuda.h>
#include <stdint.h>

typedef __nv_bfloat16 bf16;

__device__ __forceinline__ void wgmma_rl_56(float* d, uint32_t a0, uint32_t a1, uint32_t a2, uint32_t a3, uint64_t db, int sd) {
  asm volatile("{\n.reg .pred p;\nsetp.ne.b32 p, %33, 0;\n"
    "wgmma.mma_async.sync.aligned.m64n56k16.f32.bf16.bf16 {%0,%1,%2,%3,%4,%5,%6,%7,%8,%9,%10,%11,%12,%13,%14,%15,%16,%17,%18,%19,%20,%21,%22,%23,%24,%25,%26,%27}, {%28,%29,%30,%31}, %32, p, 1, 1, 1;\n}\n"
    : "+f"(d[0]),"+f"(d[1]),"+f"(d[2]),"+f"(d[3]),"+f"(d[4]),"+f"(d[5]),"+f"(d[6]),"+f"(d[7]),"+f"(d[8]),"+f"(d[9]),"+f"(d[10]),"+f"(d[11]),"+f"(d[12]),"+f"(d[13]),"+f"(d[14]),"+f"(d[15]),"+f"(d[16]),"+f"(d[17]),"+f"(d[18]),"+f"(d[19]),"+f"(d[20]),"+f"(d[21]),"+f"(d[22]),"+f"(d[23]),"+f"(d[24]),"+f"(d[25]),"+f"(d[26]),"+f"(d[27])
    : "r"(a0), "r"(a1), "r"(a2), "r"(a3), "l"(db), "r"(sd));
}
template<uint64_t CA, uint64_t CB> __device__ __forceinline__ void wgmma_ss_56(float* d, uint32_t da, uint32_t db, int sd) {
  asm volatile("{\n.reg .pred p;\n.reg .b64 a, b;\nsetp.ne.b32 p, %30, 0;\nmov.b64 a, {%28, %31};\nmov.b64 b, {%29, %32};\n"
    "wgmma.mma_async.sync.aligned.m64n56k16.f32.bf16.bf16 {%0,%1,%2,%3,%4,%5,%6,%7,%8,%9,%10,%11,%12,%13,%14,%15,%16,%17,%18,%19,%20,%21,%22,%23,%24,%25,%26,%27}, a, b, p, 1, 1, 0, 1;\n}\n"
    : "+f"(d[0]),"+f"(d[1]),"+f"(d[2]),"+f"(d[3]),"+f"(d[4]),"+f"(d[5]),"+f"(d[6]),"+f"(d[7]),"+f"(d[8]),"+f"(d[9]),"+f"(d[10]),"+f"(d[11]),"+f"(d[12]),"+f"(d[13]),"+f"(d[14]),"+f"(d[15]),"+f"(d[16]),"+f"(d[17]),"+f"(d[18]),"+f"(d[19]),"+f"(d[20]),"+f"(d[21]),"+f"(d[22]),"+f"(d[23]),"+f"(d[24]),"+f"(d[25]),"+f"(d[26]),"+f"(d[27])
    : "r"(da), "r"(db), "r"(sd), "n"((uint32_t)(CA >> 32)), "n"((uint32_t)(CB >> 32)));
}
__device__ __forceinline__ void wgmma_rl_256(float* d, uint32_t a0, uint32_t a1, uint32_t a2, uint32_t a3, uint64_t db, int sd) {
  asm volatile("{\n.reg .pred p;\nsetp.ne.b32 p, %133, 0;\n"
    "wgmma.mma_async.sync.aligned.m64n256k16.f32.bf16.bf16 {%0,%1,%2,%3,%4,%5,%6,%7,%8,%9,%10,%11,%12,%13,%14,%15,%16,%17,%18,%19,%20,%21,%22,%23,%24,%25,%26,%27,%28,%29,%30,%31,%32,%33,%34,%35,%36,%37,%38,%39,%40,%41,%42,%43,%44,%45,%46,%47,%48,%49,%50,%51,%52,%53,%54,%55,%56,%57,%58,%59,%60,%61,%62,%63,%64,%65,%66,%67,%68,%69,%70,%71,%72,%73,%74,%75,%76,%77,%78,%79,%80,%81,%82,%83,%84,%85,%86,%87,%88,%89,%90,%91,%92,%93,%94,%95,%96,%97,%98,%99,%100,%101,%102,%103,%104,%105,%106,%107,%108,%109,%110,%111,%112,%113,%114,%115,%116,%117,%118,%119,%120,%121,%122,%123,%124,%125,%126,%127}, {%128,%129,%130,%131}, %132, p, 1, 1, 1;\n}\n"
    : "+f"(d[0]),"+f"(d[1]),"+f"(d[2]),"+f"(d[3]),"+f"(d[4]),"+f"(d[5]),"+f"(d[6]),"+f"(d[7]),"+f"(d[8]),"+f"(d[9]),"+f"(d[10]),"+f"(d[11]),"+f"(d[12]),"+f"(d[13]),"+f"(d[14]),"+f"(d[15]),"+f"(d[16]),"+f"(d[17]),"+f"(d[18]),"+f"(d[19]),"+f"(d[20]),"+f"(d[21]),"+f"(d[22]),"+f"(d[23]),"+f"(d[24]),"+f"(d[25]),"+f"(d[26]),"+f"(d[27]),"+f"(d[28]),"+f"(d[29]),"+f"(d[30]),"+f"(d[31]),"+f"(d[32]),"+f"(d[33]),"+f"(d[34]),"+f"(d[35]),"+f"(d[36]),"+f"(d[37]),"+f"(d[38]),"+f"(d[39]),"+f"(d[40]),"+f"(d[41]),"+f"(d[42]),"+f"(d[43]),"+f"(d[44]),"+f"(d[45]),"+f"(d[46]),"+f"(d[47]),"+f"(d[48]),"+f"(d[49]),"+f"(d[50]),"+f"(d[51]),"+f"(d[52]),"+f"(d[53]),"+f"(d[54]),"+f"(d[55]),"+f"(d[56]),"+f"(d[57]),"+f"(d[58]),"+f"(d[59]),"+f"(d[60]),"+f"(d[61]),"+f"(d[62]),"+f"(d[63]),"+f"(d[64]),"+f"(d[65]),"+f"(d[66]),"+f"(d[67]),"+f"(d[68]),"+f"(d[69]),"+f"(d[70]),"+f"(d[71]),"+f"(d[72]),"+f"(d[73]),"+f"(d[74]),"+f"(d[75]),"+f"(d[76]),"+f"(d[77]),"+f"(d[78]),"+f"(d[79]),"+f"(d[80]),"+f"(d[81]),"+f"(d[82]),"+f"(d[83]),"+f"(d[84]),"+f"(d[85]),"+f"(d[86]),"+f"(d[87]),"+f"(d[88]),"+f"(d[89]),"+f"(d[90]),"+f"(d[91]),"+f"(d[92]),"+f"(d[93]),"+f"(d[94]),"+f"(d[95]),"+f"(d[96]),"+f"(d[97]),"+f"(d[98]),"+f"(d[99]),"+f"(d[100]),"+f"(d[101]),"+f"(d[102]),"+f"(d[103]),"+f"(d[104]),"+f"(d[105]),"+f"(d[106]),"+f"(d[107]),"+f"(d[108]),"+f"(d[109]),"+f"(d[110]),"+f"(d[111]),"+f"(d[112]),"+f"(d[113]),"+f"(d[114]),"+f"(d[115]),"+f"(d[116]),"+f"(d[117]),"+f"(d[118]),"+f"(d[119]),"+f"(d[120]),"+f"(d[121]),"+f"(d[122]),"+f"(d[123]),"+f"(d[124]),"+f"(d[125]),"+f"(d[126]),"+f"(d[127])
    : "r"(a0), "r"(a1), "r"(a2), "r"(a3), "l"(db), "r"(sd));
}
template<uint64_t CA, uint64_t CB> __device__ __forceinline__ void wgmma_ss_128(float* d, uint32_t da, uint32_t db, int sd) {
  asm volatile("{\n.reg .pred p;\n.reg .b64 a, b;\nsetp.ne.b32 p, %66, 0;\nmov.b64 a, {%64, %67};\nmov.b64 b, {%65, %68};\n"
    "wgmma.mma_async.sync.aligned.m64n128k16.f32.bf16.bf16 {%0,%1,%2,%3,%4,%5,%6,%7,%8,%9,%10,%11,%12,%13,%14,%15,%16,%17,%18,%19,%20,%21,%22,%23,%24,%25,%26,%27,%28,%29,%30,%31,%32,%33,%34,%35,%36,%37,%38,%39,%40,%41,%42,%43,%44,%45,%46,%47,%48,%49,%50,%51,%52,%53,%54,%55,%56,%57,%58,%59,%60,%61,%62,%63}, a, b, p, 1, 1, 0, 1;\n}\n"
    : "+f"(d[0]),"+f"(d[1]),"+f"(d[2]),"+f"(d[3]),"+f"(d[4]),"+f"(d[5]),"+f"(d[6]),"+f"(d[7]),"+f"(d[8]),"+f"(d[9]),"+f"(d[10]),"+f"(d[11]),"+f"(d[12]),"+f"(d[13]),"+f"(d[14]),"+f"(d[15]),"+f"(d[16]),"+f"(d[17]),"+f"(d[18]),"+f"(d[19]),"+f"(d[20]),"+f"(d[21]),"+f"(d[22]),"+f"(d[23]),"+f"(d[24]),"+f"(d[25]),"+f"(d[26]),"+f"(d[27]),"+f"(d[28]),"+f"(d[29]),"+f"(d[30]),"+f"(d[31]),"+f"(d[32]),"+f"(d[33]),"+f"(d[34]),"+f"(d[35]),"+f"(d[36]),"+f"(d[37]),"+f"(d[38]),"+f"(d[39]),"+f"(d[40]),"+f"(d[41]),"+f"(d[42]),"+f"(d[43]),"+f"(d[44]),"+f"(d[45]),"+f"(d[46]),"+f"(d[47]),"+f"(d[48]),"+f"(d[49]),"+f"(d[50]),"+f"(d[51]),"+f"(d[52]),"+f"(d[53]),"+f"(d[54]),"+f"(d[55]),"+f"(d[56]),"+f"(d[57]),"+f"(d[58]),"+f"(d[59]),"+f"(d[60]),"+f"(d[61]),"+f"(d[62]),"+f"(d[63])
    : "r"(da), "r"(db), "r"(sd), "n"((uint32_t)(CA >> 32)), "n"((uint32_t)(CB >> 32)));
}
template<uint64_t CA, uint64_t CB> __device__ __forceinline__ void wgmma_ss_64(float* d, uint32_t da, uint32_t db, int sd) {
  asm volatile("{\n.reg .pred p;\n.reg .b64 a, b;\nsetp.ne.b32 p, %34, 0;\nmov.b64 a, {%32, %35};\nmov.b64 b, {%33, %36};\n"
    "wgmma.mma_async.sync.aligned.m64n64k16.f32.bf16.bf16 {%0,%1,%2,%3,%4,%5,%6,%7,%8,%9,%10,%11,%12,%13,%14,%15,%16,%17,%18,%19,%20,%21,%22,%23,%24,%25,%26,%27,%28,%29,%30,%31}, a, b, p, 1, 1, 0, 1;\n}\n"
    : "+f"(d[0]),"+f"(d[1]),"+f"(d[2]),"+f"(d[3]),"+f"(d[4]),"+f"(d[5]),"+f"(d[6]),"+f"(d[7]),"+f"(d[8]),"+f"(d[9]),"+f"(d[10]),"+f"(d[11]),"+f"(d[12]),"+f"(d[13]),"+f"(d[14]),"+f"(d[15]),"+f"(d[16]),"+f"(d[17]),"+f"(d[18]),"+f"(d[19]),"+f"(d[20]),"+f"(d[21]),"+f"(d[22]),"+f"(d[23]),"+f"(d[24]),"+f"(d[25]),"+f"(d[26]),"+f"(d[27]),"+f"(d[28]),"+f"(d[29]),"+f"(d[30]),"+f"(d[31])
    : "r"(da), "r"(db), "r"(sd), "n"((uint32_t)(CA >> 32)), "n"((uint32_t)(CB >> 32)));
}
template<uint64_t CA, uint64_t CB> __device__ __forceinline__ void wgmma_ss_112(float* d, uint32_t da, uint32_t db, int sd) {
  asm volatile("{\n.reg .pred p;\n.reg .b64 a, b;\nsetp.ne.b32 p, %58, 0;\nmov.b64 a, {%56, %59};\nmov.b64 b, {%57, %60};\n"
    "wgmma.mma_async.sync.aligned.m64n112k16.f32.bf16.bf16 {%0,%1,%2,%3,%4,%5,%6,%7,%8,%9,%10,%11,%12,%13,%14,%15,%16,%17,%18,%19,%20,%21,%22,%23,%24,%25,%26,%27,%28,%29,%30,%31,%32,%33,%34,%35,%36,%37,%38,%39,%40,%41,%42,%43,%44,%45,%46,%47,%48,%49,%50,%51,%52,%53,%54,%55}, a, b, p, 1, 1, 0, 1;\n}\n"
    : "+f"(d[0]),"+f"(d[1]),"+f"(d[2]),"+f"(d[3]),"+f"(d[4]),"+f"(d[5]),"+f"(d[6]),"+f"(d[7]),"+f"(d[8]),"+f"(d[9]),"+f"(d[10]),"+f"(d[11]),"+f"(d[12]),"+f"(d[13]),"+f"(d[14]),"+f"(d[15]),"+f"(d[16]),"+f"(d[17]),"+f"(d[18]),"+f"(d[19]),"+f"(d[20]),"+f"(d[21]),"+f"(d[22]),"+f"(d[23]),"+f"(d[24]),"+f"(d[25]),"+f"(d[26]),"+f"(d[27]),"+f"(d[28]),"+f"(d[29]),"+f"(d[30]),"+f"(d[31]),"+f"(d[32]),"+f"(d[33]),"+f"(d[34]),"+f"(d[35]),"+f"(d[36]),"+f"(d[37]),"+f"(d[38]),"+f"(d[39]),"+f"(d[40]),"+f"(d[41]),"+f"(d[42]),"+f"(d[43]),"+f"(d[44]),"+f"(d[45]),"+f"(d[46]),"+f"(d[47]),"+f"(d[48]),"+f"(d[49]),"+f"(d[50]),"+f"(d[51]),"+f"(d[52]),"+f"(d[53]),"+f"(d[54]),"+f"(d[55])
    : "r"(da), "r"(db), "r"(sd), "n"((uint32_t)(CA >> 32)), "n"((uint32_t)(CB >> 32)));
}
__device__ __forceinline__ void wgmma_rl_112(float* d, uint32_t a0, uint32_t a1, uint32_t a2, uint32_t a3, uint64_t db, int sd) {
  asm volatile("{\n.reg .pred p;\nsetp.ne.b32 p, %61, 0;\n"
    "wgmma.mma_async.sync.aligned.m64n112k16.f32.bf16.bf16 {%0,%1,%2,%3,%4,%5,%6,%7,%8,%9,%10,%11,%12,%13,%14,%15,%16,%17,%18,%19,%20,%21,%22,%23,%24,%25,%26,%27,%28,%29,%30,%31,%32,%33,%34,%35,%36,%37,%38,%39,%40,%41,%42,%43,%44,%45,%46,%47,%48,%49,%50,%51,%52,%53,%54,%55}, {%56,%57,%58,%59}, %60, p, 1, 1, 1;\n}\n"
    : "+f"(d[0]),"+f"(d[1]),"+f"(d[2]),"+f"(d[3]),"+f"(d[4]),"+f"(d[5]),"+f"(d[6]),"+f"(d[7]),"+f"(d[8]),"+f"(d[9]),"+f"(d[10]),"+f"(d[11]),"+f"(d[12]),"+f"(d[13]),"+f"(d[14]),"+f"(d[15]),"+f"(d[16]),"+f"(d[17]),"+f"(d[18]),"+f"(d[19]),"+f"(d[20]),"+f"(d[21]),"+f"(d[22]),"+f"(d[23]),"+f"(d[24]),"+f"(d[25]),"+f"(d[26]),"+f"(d[27]),"+f"(d[28]),"+f"(d[29]),"+f"(d[30]),"+f"(d[31]),"+f"(d[32]),"+f"(d[33]),"+f"(d[34]),"+f"(d[35]),"+f"(d[36]),"+f"(d[37]),"+f"(d[38]),"+f"(d[39]),"+f"(d[40]),"+f"(d[41]),"+f"(d[42]),"+f"(d[43]),"+f"(d[44]),"+f"(d[45]),"+f"(d[46]),"+f"(d[47]),"+f"(d[48]),"+f"(d[49]),"+f"(d[50]),"+f"(d[51]),"+f"(d[52]),"+f"(d[53]),"+f"(d[54]),"+f"(d[55])
    : "r"(a0), "r"(a1), "r"(a2), "r"(a3), "l"(db), "r"(sd));
}

constexpr int DM = 448;
constexpr int NCTA = 128;
#define MAPPING 1
#define GRID 128
#define PINGPONG 0
#define WIN 6
#define WIN_END 25
#define UNR_B 1
#define UNR_C 1
constexpr int kB = UNR_B, kC = UNR_C;
#define LIKELY(x) __builtin_expect(!!(x), 1)
#define PACE 1
#define PACE_END 6
#define MAP_S 4
constexpr int SPIN_LIMIT = 1 << 22;

constexpr uint32_t OFF_X = 0, OFF_Y = 114688, OFF_MISC = 229376, SMEM_BYTES = 232448;
constexpr uint32_t Y_VR = 0, Y_K = 28672, Y_KOWN = 57344, Y_VOWN = 71680, Y_Q = 86016;
constexpr uint32_t HALF = 57344;
constexpr uint32_t X_STAT = 49152;
constexpr uint32_t M_BAR = OFF_MISC;
constexpr uint32_t M_ST = OFF_MISC + 512;
constexpr uint32_t M_G = OFF_MISC + 2304;
constexpr uint32_t M_EPOCH = OFF_MISC + 3040;
enum { B_XFULL = 0, B_FULLK = 7, B_FULLV = 8, B_FULLQ, B_KRFULL, B_VRFULL, B_WOFULL, B_XCH, B_MOD1 = 15, B_FULL = 16, B_WMFULL = 30,
       B_EMPTY = 32, B_XFREE = B_EMPTY + 12, B_GEMV, B_PEER,
       B_PUB = 47,
       B_WMFREE = 56, B_HRDY, B_GFULL = B_HRDY + 3, B_DONE = 31, B_DUMMY = B_GEMV };

__device__ uint32_t g_ticket;
__device__ __align__(128) uint32_t g_mod[8 * 6 * DM];
__device__ __align__(128) uint32_t g_flag[144 * 128];
constexpr int RB_WORDS = 262144, RB_KV = 0, RB_O = 57344, RB_X1 = 86016, RB_H2 = 143360, RB_ST = 258048;
__device__ __align__(128) uint32_t g_act[18 * RB_WORDS];
__device__ __align__(128) uint32_t g_wd[56 * 4 * 1792];
#define PROFH(id)
#define PROFH1(id)
#define PROFC(id)

struct alignas(64) Params {
    CUtensorMap wm, xm, qkv, wo, ga, ua, gb, ub, gc, uc, dn;
    const bf16 *x, *c, *wqkv, *wmod, *wg, *wu, *wd, *wop;
    bf16* out;
    uint32_t* actb;
    uint32_t zero;
};

__device__ __forceinline__ void mbar_init(uint32_t bar, int cnt) { asm volatile("mbarrier.init.shared::cta.b64 [%0], %1;" ::"r"(bar), "r"(cnt) : "memory"); }
__device__ __forceinline__ void mbar_expect_tx(uint32_t bar, uint32_t bytes) { asm volatile("mbarrier.arrive.expect_tx.shared::cta.b64 _, [%0], %1;" ::"r"(bar), "r"(bytes) : "memory"); }
__device__ __forceinline__ void mbar_arrive(uint32_t bar) { asm volatile("mbarrier.arrive.shared::cta.b64 _, [%0];" ::"r"(bar) : "memory"); }
__device__ __forceinline__ void mbar_wait(uint32_t bar, uint32_t parity) {
    uint32_t ok; int n = 0;
    do {
        asm volatile("{\n.reg .pred p;\nmbarrier.try_wait.parity.shared::cta.b64 p, [%1], %2;\nselp.u32 %0, 1, 0, p;\n}" : "=r"(ok) : "r"(bar), "r"(parity) : "memory");
        if (++n > SPIN_LIMIT) __trap();
    } while (!ok);
}
__device__ __forceinline__ void mbar_wait_c(uint32_t bar, uint32_t parity) {
    asm volatile("{\n.reg .pred p;\nWL:\nmbarrier.try_wait.parity.shared::cta.b64 p, [%0], %1, 0x989680;\n@!p bra WL;\n}" ::"r"(bar), "r"(parity) : "memory");
}
__device__ __forceinline__ void mbar_wait_cluster(uint32_t bar, uint32_t parity) {
    asm volatile("{\n.reg .pred p;\nWL:\nmbarrier.try_wait.parity.acquire.cluster.shared::cta.b64 p, [%0], %1, 0x989680;\n@!p bra WL;\n}" ::"r"(bar), "r"(parity) : "memory");
}
__device__ __forceinline__ void warp_arrive(uint32_t bar) {
    __syncwarp();
    asm volatile("{\n.reg .pred p;\nelect.sync _|p, 0xffffffff;\n@p mbarrier.arrive.shared::cta.b64 _, [%0];\n}" ::"r"(bar) : "memory");
}
__device__ __forceinline__ int opaque(int v) { return __shfl_sync(~0u, v, 0); }
__device__ __forceinline__ int fresh_tid() { int v; asm volatile("mov.u32 %0, %%tid.x;" : "=r"(v)); return v; }
__device__ __forceinline__ void bar_sync(int id, int n) { asm volatile("bar.sync %0, %1;" ::"r"(id), "r"(n) : "memory"); }
__device__ __forceinline__ void bar_arrive(int id, int n) { asm volatile("bar.arrive %0, %1;" ::"r"(id), "r"(n) : "memory"); }
__device__ __forceinline__ void fence_async_smem() { asm volatile("fence.proxy.async.shared::cta;" ::: "memory"); }
__device__ __forceinline__ void fence_async_global() { asm volatile("fence.proxy.async.global;" ::: "memory"); }
__device__ __forceinline__ void fence_gpu() { asm volatile("fence.release.gpu;" ::: "memory"); }
__device__ __forceinline__ void tma3(uint32_t dst, const CUtensorMap* m, int c0, int c1, int c2, uint32_t bar) {
    asm volatile("cp.async.bulk.tensor.3d.shared::cluster.global.mbarrier::complete_tx::bytes [%0], [%1, {%3, %4, %5}], [%2];"
                 ::"r"(dst), "l"(m), "r"(bar), "r"(c0), "r"(c1), "r"(c2) : "memory");
}
__device__ __forceinline__ void bulk_load(uint32_t dst, const void* src, uint32_t bytes, uint32_t bar) {
    asm volatile("cp.async.bulk.shared::cluster.global.mbarrier::complete_tx::bytes [%0], [%1], %2, [%3];" ::"r"(dst), "l"(src), "r"(bytes), "r"(bar) : "memory");
}
__device__ __forceinline__ void expect_e(uint32_t bar, uint32_t bytes) {
    asm volatile("{\n.reg .pred p;\nelect.sync _|p, 0xffffffff;\n@p mbarrier.arrive.expect_tx.shared::cta.b64 _, [%0], %1;\n}" ::"r"(bar), "r"(bytes) : "memory");
}
__device__ __forceinline__ void tma3_e(uint32_t dst, const CUtensorMap* m, int c0, int c1, int c2, uint32_t bar) {
    asm volatile("{\n.reg .pred p;\nelect.sync _|p, 0xffffffff;\n@p cp.async.bulk.tensor.3d.shared::cluster.global.mbarrier::complete_tx::bytes [%0], [%1, {%3, %4, %5}], [%2];\n}"
                 ::"r"(dst), "l"(m), "r"(bar), "r"(c0), "r"(c1), "r"(c2) : "memory");
}
__device__ __forceinline__ void bulk_e(uint32_t dst, const void* src, uint32_t bytes, uint32_t bar) {
    asm volatile("{\n.reg .pred p;\nelect.sync _|p, 0xffffffff;\n@p cp.async.bulk.shared::cluster.global.mbarrier::complete_tx::bytes [%0], [%1], %2, [%3];\n}"
                 ::"r"(dst), "l"(src), "r"(bytes), "r"(bar) : "memory");
}
__device__ __forceinline__ void init_e(uint32_t bar, int cnt) {
    asm volatile("{\n.reg .pred p;\nelect.sync _|p, 0xffffffff;\n@p mbarrier.init.shared::cta.b64 [%0], %1;\n}" ::"r"(bar), "r"(cnt) : "memory");
}
__device__ __forceinline__ void l2_prefetch_e(const void* src, uint32_t bytes) {
    asm volatile("{\n.reg .pred p;\nelect.sync _|p, 0xffffffff;\n@p cp.async.bulk.prefetch.L2.global [%0], %1;\n}" ::"l"(src), "r"(bytes) : "memory");
}
__device__ __forceinline__ uint32_t ld_relaxed(const uint32_t* p) { uint32_t v; asm volatile("ld.relaxed.gpu.global.u32 %0, [%1];" : "=r"(v) : "l"(p) : "memory"); return v; }
__device__ __forceinline__ void st_relaxed(uint32_t* p, uint32_t v) { asm volatile("st.relaxed.gpu.global.u32 [%0], %1;" ::"l"(p), "r"(v) : "memory"); }
__device__ __forceinline__ uint4 ld_relaxed4(const uint4* p) { uint4 v; asm volatile("ld.relaxed.gpu.global.v4.u32 {%0,%1,%2,%3}, [%4];" : "=r"(v.x), "=r"(v.y), "=r"(v.z), "=r"(v.w) : "l"(p) : "memory"); return v; }
__device__ __forceinline__ void st_relaxed4(uint4* p, uint4 v) { asm volatile("st.relaxed.gpu.global.v4.u32 [%0], {%1,%2,%3,%4};" ::"l"(p), "r"(v.x), "r"(v.y), "r"(v.z), "r"(v.w) : "memory"); }
__device__ __forceinline__ uint4 ldg_nc4(const void* p) { uint4 v; asm volatile("ld.global.nc.L1::no_allocate.v4.u32 {%0,%1,%2,%3}, [%4];" : "=r"(v.x), "=r"(v.y), "=r"(v.z), "=r"(v.w) : "l"(p)); return v; }
__device__ __forceinline__ uint32_t ldg_nc(const void* p) { uint32_t v; asm volatile("ld.global.nc.u32 %0, [%1];" : "=r"(v) : "l"(p)); return v; }
__device__ __forceinline__ uint32_t ld_acquire(const uint32_t* p) { uint32_t v; asm volatile("ld.acquire.gpu.global.u32 %0, [%1];" : "=r"(v) : "l"(p) : "memory"); return v; }
__device__ __forceinline__ uint4 lds4(uint32_t a) { uint4 v; asm volatile("ld.shared.v4.u32 {%0,%1,%2,%3}, [%4];" : "=r"(v.x), "=r"(v.y), "=r"(v.z), "=r"(v.w) : "r"(a) : "memory"); return v; }
__device__ __forceinline__ float2 lds2f(uint32_t a) { float2 v; asm volatile("ld.shared.v2.f32 {%0,%1}, [%2];" : "=f"(v.x), "=f"(v.y) : "r"(a) : "memory"); return v; }
__device__ __forceinline__ uint32_t lds1(uint32_t a) { uint32_t v; asm volatile("ld.shared.u32 %0, [%1];" : "=r"(v) : "r"(a) : "memory"); return v; }
__device__ __forceinline__ void sts4(uint32_t a, uint4 v) { asm volatile("st.shared.v4.u32 [%0], {%1,%2,%3,%4};" ::"r"(a), "r"(v.x), "r"(v.y), "r"(v.z), "r"(v.w) : "memory"); }
__device__ __forceinline__ void sts2(uint32_t a, uint32_t x, uint32_t y) { asm volatile("st.shared.v2.u32 [%0], {%1,%2};" ::"r"(a), "r"(x), "r"(y) : "memory"); }
__device__ __forceinline__ void sts1(uint32_t a, uint32_t v) { asm volatile("st.shared.u32 [%0], %1;" ::"r"(a), "r"(v) : "memory"); }
__device__ __forceinline__ void stsm4(uint32_t a, uint32_t r0, uint32_t r1, uint32_t r2, uint32_t r3) {
    asm volatile("stmatrix.sync.aligned.m8n8.x4.shared.b16 [%0], {%1,%2,%3,%4};" ::"r"(a), "r"(r0), "r"(r1), "r"(r2), "r"(r3));
}
__device__ __forceinline__ uint32_t pack2(float lo, float hi) { uint32_t r; asm("cvt.rn.bf16x2.f32 %0, %1, %2;" : "=r"(r) : "f"(hi), "f"(lo)); return r; }
__device__ __forceinline__ uint32_t pack2_relu(float lo, float hi) { uint32_t r; asm("cvt.rn.relu.bf16x2.f32 %0, %1, %2;" : "=r"(r) : "f"(hi), "f"(lo)); return r; }
__device__ __forceinline__ uint32_t hfma2(uint32_t a, uint32_t b, uint32_t c) { uint32_t r; asm("fma.rn.bf16x2 %0, %1, %2, %3;" : "=r"(r) : "r"(a), "r"(b), "r"(c)); return r; }
__device__ __forceinline__ uint32_t hmul2(uint32_t a, uint32_t b) { uint32_t r; asm("mul.rn.bf16x2 %0, %1, %2;" : "=r"(r) : "r"(a), "r"(b)); return r; }
__device__ __forceinline__ float bf_lo(uint32_t v) { return __uint_as_float(v << 16); }
__device__ __forceinline__ float bf_hi(uint32_t v) { return __uint_as_float(v & 0xFFFF0000u); }
__device__ __forceinline__ float bf_round(float v) { return bf_lo(pack2(v, 0.f)); }
__device__ __forceinline__ float ex2(float x) { float r; asm("ex2.approx.ftz.f32 %0, %1;" : "=f"(r) : "f"(x)); return r; }
__device__ __forceinline__ void mma16816(float* d, uint32_t a0, uint32_t a1, uint32_t a2, uint32_t a3, uint32_t b0, uint32_t b1) {
    asm("mma.sync.aligned.m16n8k16.row.col.f32.bf16.bf16.f32 {%0,%1,%2,%3}, {%4,%5,%6,%7}, {%8,%9}, {%0,%1,%2,%3};"
        : "+f"(d[0]), "+f"(d[1]), "+f"(d[2]), "+f"(d[3]) : "r"(a0), "r"(a1), "r"(a2), "r"(a3), "r"(b0), "r"(b1));
}
__device__ __forceinline__ void mma16816_first(float* d, uint32_t a0, uint32_t a1, uint32_t a2, uint32_t a3, uint32_t b0, uint32_t b1) {
    asm volatile("mma.sync.aligned.m16n8k16.row.col.f32.bf16.bf16.f32 {%0,%1,%2,%3}, {%4,%5,%6,%7}, {%8,%9}, {%10,%10,%10,%10};"
        : "=f"(d[0]), "=f"(d[1]), "=f"(d[2]), "=f"(d[3]) : "r"(a0), "r"(a1), "r"(a2), "r"(a3), "r"(b0), "r"(b1), "f"(0.f));
}
__device__ __forceinline__ void mma16816_v(float* d, uint32_t a0, uint32_t a1, uint32_t a2, uint32_t a3, uint32_t b0, uint32_t b1) {
    asm volatile("mma.sync.aligned.m16n8k16.row.col.f32.bf16.bf16.f32 {%0,%1,%2,%3}, {%4,%5,%6,%7}, {%8,%9}, {%0,%1,%2,%3};"
        : "+f"(d[0]), "+f"(d[1]), "+f"(d[2]), "+f"(d[3]) : "r"(a0), "r"(a1), "r"(a2), "r"(a3), "r"(b0), "r"(b1));
}
__device__ __forceinline__ void mma1688(float* d, uint32_t a0, uint32_t a1, uint32_t b0) {
    asm("mma.sync.aligned.m16n8k8.row.col.f32.bf16.bf16.f32 {%0,%1,%2,%3}, {%4,%5}, {%6}, {%0,%1,%2,%3};"
        : "+f"(d[0]), "+f"(d[1]), "+f"(d[2]), "+f"(d[3]) : "r"(a0), "r"(a1), "r"(b0));
}
__device__ __forceinline__ void ldsm4(uint32_t a, uint32_t* r) {
    asm volatile("ldmatrix.sync.aligned.m8n8.x4.shared.b16 {%0,%1,%2,%3}, [%4];" : "=r"(r[0]), "=r"(r[1]), "=r"(r[2]), "=r"(r[3]) : "r"(a));
}
__device__ __forceinline__ void ldsm4t(uint32_t a, uint32_t* r) {
    asm volatile("ldmatrix.sync.aligned.m8n8.x4.trans.shared.b16 {%0,%1,%2,%3}, [%4];" : "=r"(r[0]), "=r"(r[1]), "=r"(r[2]), "=r"(r[3]) : "r"(a));
}
__device__ __forceinline__ uint32_t nz(uint32_t v) { uint32_t r; asm("max.u32 %0, %1, 1;" : "=r"(r) : "r"(v)); return r; }
__device__ __forceinline__ float rcp(float x) { float r; asm("rcp.approx.ftz.f32 %0, %1;" : "=f"(r) : "f"(x)); return r; }
__device__ __forceinline__ uint2 ld_relaxed2(const void* p) { uint2 v; asm volatile("ld.relaxed.gpu.global.v2.u32 {%0,%1}, [%2];" : "=r"(v.x), "=r"(v.y) : "l"(p) : "memory"); return v; }
__device__ __forceinline__ void st_relaxed2(void* p, uint32_t x, uint32_t y) { asm volatile("st.relaxed.gpu.global.v2.u32 [%0], {%1,%2};" ::"l"(p), "r"(max(x, 1u)), "r"(max(y, 1u)) : "memory"); }
__host__ __device__ constexpr uint64_t dconst(uint32_t lbo, uint32_t sbo, uint32_t swz) {
    return ((uint64_t)(lbo >> 4) << 16) | ((uint64_t)(sbo >> 4) << 32) | ((uint64_t)swz << 62);
}
__device__ __forceinline__ uint32_t mkdesc(uint32_t addr, uint64_t c) { return (uint32_t)c | ((addr & 0x3FFFF) >> 4); }
#define WG_FENCE() asm volatile("wgmma.fence.sync.aligned;" ::: "memory")
#define WG_COMMIT() asm volatile("wgmma.commit_group.sync.aligned;" ::: "memory")
#define WG_WAIT(n) asm volatile("wgmma.wait_group.sync.aligned %0;" ::"n"(n) : "memory")
template <int N> __device__ __forceinline__ void reg_fence(float* d) {
#pragma unroll
    for (int i = 0; i < N; i++) asm volatile("" : "+f"(d[i])::"memory");
}
template <int N> __device__ __forceinline__ void reg_def(float* d) {
#pragma unroll
    for (int i = 0; i < N; i++) asm volatile("" : "=f"(d[i]));
}
template <int N> __device__ __forceinline__ void reg_def(uint32_t* d) {
#pragma unroll
    for (int i = 0; i < N; i++) asm volatile("" : "=r"(d[i]));
}
__device__ __forceinline__ bool is_unset(uint4 v) { return min(min(v.x, v.y), min(v.z, v.w)) == 0u; }
__device__ __forceinline__ uint4 nz4(uint32_t a, uint32_t b, uint32_t c, uint32_t d) { return make_uint4(max(a, 1u), max(b, 1u), max(c, 1u), max(d, 1u)); }
__device__ __forceinline__ void wait_flags(const uint32_t* p, uint32_t target, uint32_t mask) {
    int n = 0;
    while (~__ballot_sync(~0u, (int)(ld_relaxed(p) - target) >= 0) & mask) { if (++n > SPIN_LIMIT) __trap(); }
    asm volatile("fence.acquire.gpu;" ::: "memory");
}
__device__ __forceinline__ float silu_bf(uint32_t cbits) {
    const float c = __uint_as_float(cbits << 16);
    return bf_round(__fdividef(c, 1.f + fminf(ex2(-1.4426950408889634f * c), 1e30f)));
}
__device__ __forceinline__ void gemv_part(uint32_t wmbuf, int npanel, int wp, int lane) {
    const uint32_t wa = wmbuf + wp * 512 + (8 * (lane >> 4) + (lane & 7)) * 32 + ((lane >> 3) & 1) * 16;
    uint2 B[4];
#pragma unroll
    for (int i = 0; i < 4; i++) { const float2 v = lds2f(wmbuf + 28672 + (wp + 8 * i) * 32 + (lane & 3) * 8); B[i] = make_uint2(__float_as_uint(v.x), __float_as_uint(v.y)); }
#pragma unroll 1
    for (int pn = 0; pn < npanel; pn++) {
        float d[4] = {};
        uint32_t A[16];
#pragma unroll
        for (int i = 0; i < 4; i++) ldsm4t(wa + pn * 14336 + (i < 3 || wp < 4 ? i : 0) * 4096, A + 4 * i);
#pragma unroll
        for (int i = 0; i < 4; i++) mma16816(d, A[4 * i], A[4 * i + 1], A[4 * i + 2], A[4 * i + 3], B[i].x, B[i].y);
        if ((lane & 3) == 0) {
            sts1(wmbuf + 29696 + (wp * 32 + pn * 16 + (lane >> 2)) * 4, __float_as_uint(d[0]));
            sts1(wmbuf + 29696 + (wp * 32 + pn * 16 + 8 + (lane >> 2)) * 4, __float_as_uint(d[2]));
        }
    }
}
__device__ __forceinline__ const uint4* mod_src(int i, int r, int j, bool p2) {
    i = min(i, p2 ? 251 : 223);
    return (const uint4*)g_mod + (r & 7) * (6 * DM / 4) + (i < 224 ? (p2 ? 336 : 0) + i : (i < 238 ? 14 * j + i : 14 * j + i + 322));
}
__device__ __forceinline__ void mod_store(uint32_t sb, uint4 v, const uint4* src, int i, uint32_t sc) {
    const uint32_t tag = lds1(sb + M_EPOCH) + 1;
    while (__any_sync(~0u, (((v.x ^ tag) | (v.y ^ tag) | (v.z ^ tag) | (v.w ^ tag)) & 0xFFFFu) != 0u) && !sc) v = ld_relaxed4(src);
    if (i < 224) {
        const int isc = i >= 112, c4 = i - 112 * isc;
        const uint32_t a = sb + M_ST + (c4 >> 2) * 64 + (c4 & 1) * 32 + (c4 & 2) * 4 + (isc ? 0 : 4);
        sts1(a, __byte_perm(v.x, v.y, 0x7632));
        sts1(a + 16, __byte_perm(v.z, v.w, 0x7632));
    } else if (i < 252) {
        sts4(sb + M_G + (i - 224) * 16, make_uint4(v.x & 0xFFFF0000u, v.y & 0xFFFF0000u, v.z & 0xFFFF0000u, v.w & 0xFFFF0000u));
    }
}
__device__ __forceinline__ int pass_f(int fs, int ps) { return 224 * fs + ((fs & 1) ? (ps == 0 ? 96 : ps == 1 ? 32 : 0) : (ps == 0 ? 0 : ps == 1 ? 128 : 192)); }
__device__ __forceinline__ constexpr uint32_t slot_off(int l) { return l * 16384; }
__device__ __forceinline__ constexpr int g1_slot(int s) { return s % 7; }
__device__ __noinline__ void x1_fix(const uint32_t* g, uint32_t sa, int s) {
#pragma unroll 1
    for (int k = 4 * s; k < 4 * s + 4;) {
        const uint4 v = ld_relaxed4((const uint4*)(g + k * 256));
        sts4(sa + k * 1024, v);
        k += 2 * __all_sync(~0u, min(min(v.x, v.y), min(v.z, v.w)) != 0u);
    }
    __syncwarp();
}
__device__ __forceinline__ void ln_coeffs(float mean, float msq, uint32_t& r2, uint32_t& n2) {
    const float rs = bf_round(rsqrtf(fmaxf(msq - mean * mean, 0.f) + 1e-5f));
    r2 = pack2(rs, rs);
    n2 = pack2(-mean * rs, -mean * rs);
}

#define LOADW bulk_e(dst, g_wd + (size_t)((f >> 5) * 4 + nq) * 1792, 7168, bar);
template <int sec> __device__ __forceinline__ void ring_loader(const Params& p, uint32_t sb_, int r_, int j_, int lane) {
    const uint32_t sb = opaque(sb_);
    const int r = opaque(r_), j = opaque(j_), nq = j >> 1, fs = 4 * (j & 1) + nq;
    const int fa = pass_f(fs, 0), fb = pass_f(fs, 1), fc = pass_f(fs, 2);
    const uint32_t* h2src = (const uint32_t*)__shfl_sync(~0u, (unsigned long long)(p.actb + (size_t)r * RB_WORDS + RB_H2), 0);
    const CUtensorMap* gmap = (const CUtensorMap*)__shfl_sync(~0u, (unsigned long long)(&p.ga + sec), 0);
#define BAR(i) (sb + M_BAR + 8 * (i))
#define kh (j & 1)
            int sl = 0;
            mbar_wait(BAR(B_PUB + 2), 0);
            wait_flags(g_flag + (8 * r + j) * 128 + 96 + lane, lds1(sb + M_EPOCH) + 1, 0xFFFFu);
            fence_async_global();
#pragma unroll 1
            for (int s = 0; s < 28; s++) {
                const int ps = s < 14 ? 0 : s < 21 ? 1 : 2;
                const uint32_t half = ps < 2 ? 8192 : 4096;
                const int sp = sl;
                if (s >= PACE && s < PACE_END) mbar_wait(BAR(B_FULL + s - PACE), 0);
                mbar_wait(BAR(B_EMPTY + sp), (s >= 7 && s < 14) || s >= 21);
                expect_e(BAR(B_FULL + sp), half);
                tma3_e(sb + slot_off(sp) + sec * half, gmap + 2 * ps, 0, ps ? 64 * sl : 32 * s, ps == 0 ? fa >> 6 : ps == 1 ? fb >> 6 : fc >> 5, BAR(B_FULL + sp));
                sl = sl == 6 ? 0 : sl + 1;
            }
            if (!sec) PROFH(3);
#pragma unroll 1
            for (int e = 0; e < 4; e++) {
                const uint32_t dst = sb + slot_off(e) + sec * 8192, bar = BAR(B_FULL + e);
                const int f = (e < 2 ? fa + 64 * e : e == 2 ? fb : fc) + 32 * sec;
                mbar_wait(BAR(B_EMPTY + e), 0);
                expect_e(bar, e == 3 && sec ? 0 : 7168);
                if (!(e == 3 && sec)) { LOADW }
            }
            sl = 4;
            int e = 4;
#pragma unroll 1
            for (int grp = 0; grp < 9; grp++) {
                const int ps = grp >= 6 ? 2 : grp >= 3 ? 1 : 0;
                int sidx = grp - 3 * ps;
                if (sec && sidx == 0) { mbar_wait(BAR(B_HRDY + ps), 0); fence_async_global(); }
                sidx += sidx >= nq;
                int f = pass_f(4 * kh + sidx, ps);
#pragma unroll 1
                for (int k = 4 >> ps; k > 0; k--, e++, f += 32) {
                    const uint32_t dst = sb + slot_off(sl), bar = BAR(B_FULL + sl);
                    mbar_wait(BAR(B_EMPTY + sl), e >= 12 && e < 24);
                    if (e < WIN_END && e >= WIN) mbar_wait(BAR(B_FULL + (sl >= WIN ? sl - WIN : sl + 12 - WIN)), e - WIN >= 12);
                    expect_e(bar, sec ? 8192 : 7168);
                    if (!sec) { LOADW }
                    else bulk_e(dst + 8192, h2src + f * 64, 8192, bar);
                    sl = sl == 11 ? 0 : sl + 1;
                }
            }
            if (!sec) PROFH(4);
}

#define PROF_PARAMS
#define PROF_ARGS
__device__ __noinline__ void helper_late(const Params& p, int r_, int j_, int warp_ PROF_PARAMS) {
    extern __shared__ __align__(1024) unsigned char smem[];
    const uint32_t sb = (uint32_t)__cvta_generic_to_shared(smem);
    const int r = opaque(r_), j = opaque(j_), warp = opaque(warp_), nq = j >> 1, b = 8 * r + j;
    uint32_t* const act = (uint32_t*)__shfl_sync(~0u, (unsigned long long)(p.actb + (size_t)r * RB_WORDS), 0);
    {
        const int lane = fresh_tid() & 31;
        const uint32_t target = lds1(sb + M_EPOCH) + 1;
        if (warp == 8) { expect_e(BAR(B_XCH), 14336); expect_e(BAR(B_XCH + 1), 14336); }
            if (warp == 9) {
#pragma unroll 1
                for (int kv = 0; kv < 2; kv++) {
                    mbar_wait(BAR(B_PUB + kv), 0);
                    wait_flags(g_flag + b * 128 + lane, target, (r >= 2 ? 6u : r == 1 ? 2u : 0u) << (8 * kv));
                    fence_async_global();
                    const uint32_t dst = sb + OFF_Y + (kv ? Y_VR : Y_K);
                    expect_e(BAR(B_KRFULL + kv), r >= 2 ? 28672 : r == 1 ? 14336 : 0);
                    if (r >= 2) bulk_e(dst, act - 2 * RB_WORDS + RB_KV + j * 7168 + kv * 3584, 14336, BAR(B_KRFULL + kv));
                    if (r >= 1) bulk_e(dst + 14336, act - RB_WORDS + RB_KV + j * 7168 + kv * 3584, 14336, BAR(B_KRFULL + kv));
                }
            } else if (warp == 11) {
                mbar_wait(BAR(B_VRFULL), 0);
                l2_prefetch_e((const char*)p.wg + (size_t)b * 12544, 12544);
                l2_prefetch_e((const char*)p.wu + (size_t)b * 12544, 12544);
#pragma unroll 1
                for (int k = 0; k < (r < 12 ? 2 : 1); k++) {
                    const int u = 28 * kh + r + 16 * k;
                    expect_e(BAR(B_XFULL + k), 7168);
                    tma3_e(sb + OFF_Y + 102400, &p.dn, 0, 32 * u, 7 * j, BAR(B_XFULL + k));
                    tma3_e(sb + OFF_Y + 102400 + 3584, &p.dn, 0, 32 * u, 7 * (j ^ 1), BAR(B_XFULL + k));
                    mbar_wait(BAR(B_XFULL + k), 1);
                    asm volatile("{\n.reg .pred p;\nelect.sync _|p, 0xffffffff;\n@p cp.async.bulk.global.shared::cta.bulk_group [%0], [%1], 7168;\n"
                                 "cp.async.bulk.commit_group;\ncp.async.bulk.wait_group 0;\n}" ::"l"(g_wd + (size_t)(u * 4 + nq) * 1792), "r"(sb + OFF_Y + 102400) : "memory");
                    __syncwarp();
                }
                warp_arrive(BAR(B_WMFREE));
                fence_gpu();
                if (lane < 16) st_relaxed(g_flag + (8 * lane + j) * 128 + 96 + r, target);
            }
        if (warp == 8 || warp == 11) {
            const int sec = warp == 11;
            if (sec) ring_loader<1>(p, sb, r, j, lane); else ring_loader<0>(p, sb, r, j, lane);
            mbar_wait(BAR(B_DONE), 0);
        } else if (warp == 9) {
#pragma unroll
            for (int ev = 0; ev < 4; ev++) { expect_e(BAR(B_GFULL + ev), ev < 2 ? HALF / 2 : 16384 + 4096); expect_e(BAR(B_XFULL + 2 + ev), ev < 2 ? HALF / 2 : HALF - 16384); }
            mbar_wait(BAR(B_PUB + 2), 0);
            const uint32_t* fp = g_flag + b * 128 + 32 + lane;
            const int par = (target - 1) & 1;
#pragma unroll 1
            for (int n = 0, ev = 0; ev < 4; n++) {
                if (ev == 1) { mbar_wait(BAR(B_WMFREE), 1); mbar_wait(BAR(B_PUB + 3), 0); }
                uint32_t ok = __ballot_sync(~0u, (int)(ld_relaxed(fp) - target) >= 0) >> (8 * ev);
                while ((ok & 0xFFu) == 0xFFu) {
                    asm volatile("fence.acquire.gpu;" ::: "memory");
                    fence_async_global();
                    const int tile = (ev & 1) + (ev >> 1) * par * 2;
                    const uint32_t dst = sb + (ev == 0 ? OFF_X : OFF_Y + (ev & 1) * HALF), first = ev < 2 ? HALF / 2 : 16384;
                    const char* src = (const char*)(act + RB_O + ((ev >> 1) * 2 + tile) * 14336);
                    if (ev >= 2) bulk_e(sb + OFF_X + X_STAT + (ev & 1) * 49152, act + RB_ST + tile * 1024, 4096, BAR(B_GFULL + ev));
                    bulk_e(dst, src, first, BAR(B_GFULL + ev));
                    bulk_e(dst + first, src + first, HALF - first, BAR(B_XFULL + 2 + ev));
                    if (ev) PROFH(4 + ev);
                    ev++; ok >>= 8;
                }
                if (n > SPIN_LIMIT) __trap();
            }
            mbar_wait(BAR(B_XFULL + 5), 1);
#pragma unroll 1
            for (int hf = 0; hf < 2; hf++) {
                const int tile = (par ^ 1) * 2 + hf;
                uint4* xz = (uint4*)(act + RB_X1 + tile * 14336 + j * 1792) + lane;
#pragma unroll
                for (int i = 0; i < 14; i++) xz[i * 32] = make_uint4(0, 0, 0, 0);
                ((uint4*)(act + RB_ST + (tile * 8 + j) * 128))[lane] = make_uint4(0, 0, 0, 0);
            }
#pragma unroll 1
            for (int ps = 0; ps < 3; ps++) {
                mbar_wait(BAR(B_PUB + 6 + ps), 0);
                wait_flags(g_flag + b * 128 + 64 + lane, target, (0x55u << kh) << (8 * ps));
                warp_arrive(BAR(B_HRDY + ps));
                PROFH(9 + ps);
            }
        } else {
#pragma unroll 1
            for (int k = 0; k < 9; k++) {
                uint32_t* fp = k < 2 ? g_flag + (b + 8 * lane) * 128 + k * 8 + lane : g_flag + (8 * r + lane) * 128 + 16 + k * 8 + j;
                mbar_wait(BAR(B_PUB + k), 0);
                if (k != 4 && k != 5) fence_gpu();
                if (k < 2 ? (lane == 1 || lane == 2) : lane < 8) st_relaxed(fp, target);
                if (k >= 3 && k <= 5) PROFH(k - 3);
            }
        }
    }
}

__global__ void __cluster_dims__(2, 1, 1) __launch_bounds__(384, 1) fused_block_kernel(const __grid_constant__ Params p) {
    extern __shared__ __align__(1024) unsigned char smem[];
    const uint32_t sb = (uint32_t)__cvta_generic_to_shared(smem);
    const int tid = threadIdx.x, lane = tid & 31, warp = __shfl_sync(~0u, tid >> 5, 0);
    const int m = blockIdx.x >> 1;
    int r, nq;
    if (m < 4) { r = 15; nq = m; }
    else if (m < 36) { r = (m - 4) & 7; nq = (m - 4) >> 3; }
    else { nq = (m - 36) / 7; r = m - 28 - 7 * nq; }
    const int j = opaque(2 * nq + (blockIdx.x & 1)), b = 8 * r + j, fs = 4 * kh + nq;
#define act (p.actb + (size_t)r * RB_WORDS)
    constexpr uint32_t sc = 0;
    if (lane == 0 && warp < 9 && warp != 6 && warp != 7) {
        const int i0 = warp == 8 ? 0 : 8 + 8 * warp, cnt = warp == 0 || warp == 8 ? 1 : warp < 3 ? 2 : 8;
#pragma unroll
        for (int k = 0; k < 8; k++) if (i0 + k != B_WMFULL) mbar_init(BAR(i0 + k), cnt);
        asm volatile("fence.mbarrier_init.release.cluster;" ::: "memory");
        fence_async_smem();
    }

    if (warp >= 8) {
        const int lane = fresh_tid() & 31;
        const bool early = kh == 0, gemv = r < 14;
        const int mcol = early ? 16 * (4 * r + nq) : 2 * DM + 32 * (4 * r + nq);
        const uint32_t wmbuf = sb + OFF_Y + HALF;
        asm volatile("setmaxnreg.dec.sync.aligned.u32 56;");
        if (warp == 9) {
#pragma unroll
            for (int i = 56; i < 64; i++) init_e(BAR(i), 1);
            fence_async_smem();
        }
        if (warp == 8) { init_e(BAR(B_WMFULL), 1); fence_async_smem(); }
        bar_arrive(0, 384);
        asm volatile("barrier.cluster.arrive.relaxed.aligned;" ::: "memory");
        if (warp == 8) {
            if (!sc) {
                expect_e(BAR(B_WMFULL), gemv ? 28672 >> early : 0);
                if (early && gemv) { tma3_e(wmbuf, &p.wm, mcol, 0, 0, BAR(B_WMFULL)); tma3_e(wmbuf + 7168, &p.wm, mcol, 224, 0, BAR(B_WMFULL)); }
#pragma unroll 1
                for (int kb = 0; kb < 7; kb++) {
                    expect_e(BAR(B_XFULL + kb), 16384);
                    tma3_e(sb + OFF_X + kb * 16384, &p.xm, 64 * kb, 128 * r, 0, BAR(B_XFULL + kb));
                }
            }
#pragma unroll 1
            for (int mt = 0; mt < 4; mt++) {
                if (mt == 1) {
                    if (!early && gemv) {
#pragma unroll 1
                        for (int k = 0; k < 4; k++) tma3_e(wmbuf + k * 7168, &p.wm, mcol + (k >> 1) * 16, (k & 1) * 224, 0, BAR(B_WMFULL));
                    }
                    bar_sync(9, 384);
                    if (sc) return;
                    mbar_wait(BAR(B_WMFREE), 0);
                }
                if (mt) mbar_wait(BAR(mt == 1 ? B_MOD1 : mt == 2 ? B_XFREE : B_VRFULL), 0);
                const uint32_t bar = BAR(mt == 3 ? B_WOFULL : B_FULLK + mt), dst = sb + (mt < 2 ? OFF_Y : OFF_X) + (mt & 1) * HALF;
                const int c0 = (mt < 2 ? DM + DM * mt : 0) + 56 * j - 8 * kh;
                if (!sc) {
                    expect_e(bar, HALF);
                    tma3_e(dst, mt == 3 ? &p.wo : &p.qkv, c0, 0, 0, bar);
                    tma3_e(dst + HALF / 2, mt == 3 ? &p.wo : &p.qkv, c0, 224, 0, bar);
                }
            }
        } else {
            if (warp == 10 && !sc) l2_prefetch_e((const char*)p.wqkv + (size_t)b * 9408, 9408);
            bar_sync(9, 384);
            if (sc) return;
            if (warp == 11) {
                const int col = mcol + (early ? lane & 15 : lane);
                const uint32_t tag = (lds1(sb + M_EPOCH) + 1) & 0xFFFFu;
                mbar_wait(BAR(B_GEMV), 0);
                float sum = 0.f;
#pragma unroll
                for (int i = 0; i < 8; i++) sum += *(const float*)(smem + OFF_Y + HALF + 29696 + (i * 32 + col - mcol) * 4);
                sum = bf_round(sum);
                if ((col >= DM && col < 2 * DM) || (col >= 4 * DM && col < 5 * DM)) sum += 1.f;
                uint32_t* mg = g_mod + col + (early ? (lane >> 4) * 4 * 6 * DM : 0);
#pragma unroll 1
                for (int i = gemv ? (early ? 4 : 8) : 0; i > 0; i--, mg += 6 * DM) st_relaxed(mg, (pack2(sum, 0.f) << 16) | tag);
                warp_arrive(BAR(B_WMFREE));
            }
        }
    }
    if (LIKELY(warp < 8)) {
        const int w = warp >> 2, wi = warp & 3;
#define COORDS const int t = fresh_tid() & 127, lane = t & 31, q = lane & 3, lr = lane >> 2, ra = 64 * w + 16 * wi + lr; \
        const uint32_t lx = (lane >> 4) ^ (lane & 7), mrow = (64 * w + 16 * wi + ((lane >> 3) & 1) * 8 + (lane & 7)) * 128; \
        (void)q; (void)lr; (void)ra; (void)lx; (void)mrow;
        const int sid = 2 * (j & 3) + w;
#define RUN(k) (!sc || sid == (k))
#define WAIT(i, par) mbar_wait_c(BAR(i), (par) | sc)
        constexpr uint64_t DB128 = dconst(4096, 1024, 1);
        {
            const int wd = fresh_tid();
            const uint32_t cb = wd < 224 ? __ldg((const uint32_t*)p.c + wd) : 0u;
            if (wd == 255 && !sc) sts1(sb + M_EPOCH, atomicAdd(&g_ticket, 1u) / NCTA);
            sts1(sb + OFF_Y + HALF + 28672 + (wd >> 3) * 32 + (wd & 3) * 8 + (wd & 4), pack2(silu_bf(cb & 0xFFFFu), silu_bf(cb >> 16)));
        }
        bar_arrive(9, 384);
        bar_sync(0, 384);
        asm volatile("barrier.cluster.arrive.relaxed.aligned;" ::: "memory");
        asm volatile("setmaxnreg.inc.sync.aligned.u32 224;");
        PROFC(0);
        uint32_t xr[16];
        {
            COORDS
            uint32_t h[112];
            reg_def<112>(h); reg_def<16>(xr);
#pragma unroll 1
            for (int step = 0; step < 2; step++) {
                if (step == kh) { WAIT(B_WMFULL, 0); gemv_part(sb + OFF_Y + HALF, 1 + kh, warp, lane); warp_arrive(BAR(B_GEMV)); }
                if (step) break;
                float ds[4] = {}, da[2][4] = {}, db[2][4] = {};
                const uint32_t ONE2 = 0x3F803F80u;
#pragma unroll
                for (int kb = 0; kb < 7; kb++) {
                    WAIT(B_XFULL + kb, 0);
#pragma unroll
                    for (int k4 = 0; k4 < 4; k4++) ldsm4(sb + OFF_X + mrow + kb * 16384 + (((2 * k4) ^ lx) << 4), h + 16 * kb + 4 * k4);
#pragma unroll
                    for (int k4 = 0; k4 < 4; k4++) {
                        const uint32_t* f = h + 16 * kb + 4 * k4;
                        mma16816(ds, f[0], f[1], f[2], f[3], ONE2, ONE2);
                        mma1688(da[0], f[0], f[1], f[0]); mma1688(db[0], f[0], f[1], f[1]);
                        mma1688(da[1], f[2], f[3], f[2]); mma1688(db[1], f[2], f[3], f[3]);
                    }
                }
#pragma unroll
                for (int i = 0; i < 4; i++) {
                    const int ch = 7 * j + 2 * i + (lane >> 4);
                    ldsm4(sb + OFF_X + mrow + (ch >> 3) * 16384 + (((ch ^ lane) & 7) << 4), xr + 4 * i);
                }
                warp_arrive(BAR(B_XFREE));
                float qa = (lr & 1) ? da[0][1] + da[1][1] : da[0][0] + da[1][0];
                float qb = (lr & 1) ? db[0][3] + db[1][3] : db[0][2] + db[1][2];
                const int src = (lane & ~3) | (lr >> 1);
                qa = __shfl_sync(~0u, qa, src);
                qb = __shfl_sync(~0u, qb, src);
                uint32_t ra2, na2, rb2, nb2;
                ln_coeffs(ds[0] * (1.f / DM), qa * (1.f / DM), ra2, na2);
                ln_coeffs(ds[2] * (1.f / DM), qb * (1.f / DM), rb2, nb2);
#pragma unroll
                for (int i = 0; i < 112; i += 2) { h[i] = hfma2(h[i], ra2, na2); h[i + 1] = hfma2(h[i + 1], rb2, nb2); }
            }
            PROFC(1);
            if (RUN(1)) {
                float ak[28], av[28], aq[28];
                uint32_t kp[14], vp[14];
                const uint64_t bq0 = (DB128 & ~0xFFFFFFFFull) | (mkdesc(sb + OFF_X, DB128) + kh), bk0 = bq0 + (OFF_Y >> 4), bv0 = bk0 + (HALF >> 4);
                uint32_t* kvg = act + RB_KV + j * 7168 + (8 * w + 2 * wi) * 224 + lane;
                {
                    const int i = min(fresh_tid(), 223);
                    const uint4* src = mod_src(i, r, j, false);
                    mod_store(sb, ld_relaxed4(src), src, i, sc);
                    if (!sc) bar_sync(3, 256);
                    if (warp == 0) warp_arrive(BAR(B_MOD1));
                }
                WAIT(B_FULLK, 0);
                PROFC(2);
                reg_def<28>(ak);
#pragma unroll
                for (int g4 = 0; g4 < 4; g4++) {
#pragma unroll
                    for (int ks = 7 * g4; ks < 7 * g4 + 7; ks++) {
                        const uint4 st = *(const uint4*)(smem + M_ST + ks * 64 + q * 16);
                        h[4 * ks] = hfma2(h[4 * ks], st.x, st.y); h[4 * ks + 1] = hfma2(h[4 * ks + 1], st.x, st.y);
                        h[4 * ks + 2] = hfma2(h[4 * ks + 2], st.z, st.w); h[4 * ks + 3] = hfma2(h[4 * ks + 3], st.z, st.w);
                    }
                    WG_FENCE();
#pragma unroll
                    for (int ks = 7 * g4; ks < 7 * g4 + 7; ks++) wgmma_rl_56(ak, h[4 * ks], h[4 * ks + 1], h[4 * ks + 2], h[4 * ks + 3], bk0 + ks * 128, ks != 0);
                }
                WG_COMMIT();
                PROFC(3);
                WAIT(B_FULLV, 0);
                reg_def<28>(av);
                WG_FENCE();
#pragma unroll
                for (int ks = 0; ks < 8; ks++) wgmma_rl_56(av, h[4 * ks], h[4 * ks + 1], h[4 * ks + 2], h[4 * ks + 3], bv0 + ks * 128, ks != 0);
                WG_COMMIT();
                WG_WAIT(1);
                reg_fence<28>(ak);
#pragma unroll
                for (int g = 0; g < 7; g++) {
                    kp[2 * g] = pack2(ak[4 * g], ak[4 * g + 1]); kp[2 * g + 1] = pack2(ak[4 * g + 2], ak[4 * g + 3]);
                    kvg[g * 32] = kp[2 * g]; kvg[224 + g * 32] = kp[2 * g + 1];
                }
                warp_arrive(BAR(B_PUB));
                PROFC(4);
                WG_FENCE();
#pragma unroll
                for (int ks = 8; ks < 28; ks++) wgmma_rl_56(av, h[4 * ks], h[4 * ks + 1], h[4 * ks + 2], h[4 * ks + 3], bv0 + ks * 128, 1);
                WG_COMMIT();
                WAIT(B_FULLQ, 0);
                reg_def<28>(aq);
                WG_FENCE();
#pragma unroll
                for (int ks = 0; ks < 8; ks++) wgmma_rl_56(aq, h[4 * ks], h[4 * ks + 1], h[4 * ks + 2], h[4 * ks + 3], bq0 + ks * 128, ks != 0);
                WG_COMMIT();
                WG_WAIT(1);
                reg_fence<28>(av);
#pragma unroll
                for (int g = 0; g < 7; g++) {
                    vp[2 * g] = pack2(av[4 * g], av[4 * g + 1]); vp[2 * g + 1] = pack2(av[4 * g + 2], av[4 * g + 3]);
                    kvg[3584 + g * 32] = vp[2 * g]; kvg[3584 + 224 + g * 32] = vp[2 * g + 1];
                }
                warp_arrive(BAR(B_PUB + 1));
                const uint4* msrc = mod_src(128 * w + t, r, j, true);
                const uint4 mv = ld_relaxed4(msrc);
                PROFC(5);
                WG_FENCE();
#pragma unroll
                for (int ks = 8; ks < 28; ks++) wgmma_rl_56(aq, h[4 * ks], h[4 * ks + 1], h[4 * ks + 2], h[4 * ks + 3], bq0 + ks * 128, 1);
                WG_COMMIT();
                WAIT(B_PUB + 1, 0);
                mod_store(sb, mv, msrc, 128 * w + t, sc);
                const uint32_t rg = 8 * w + 2 * wi + ((lane >> 3) & 1);
                const uint32_t ko = sb + OFF_Y + Y_KOWN + rg * 896 + (lane & 7) * 16, qo = sb + OFF_Y + Y_Q + rg * 1024 + (lane >> 4) * 128 + (lane & 7) * 16;
#pragma unroll
                for (int g = 0; g < 6; g += 2) {
                    stsm4(ko + (g + (lane >> 4)) * 128, kp[2 * g], kp[2 * g + 1], kp[2 * g + 2], kp[2 * g + 3]);
                    stsm4(ko + (Y_VOWN - Y_KOWN) + (g + (lane >> 4)) * 128, vp[2 * g], vp[2 * g + 1], vp[2 * g + 2], vp[2 * g + 3]);
                }
                stsm4(ko + (lane >> 4) * (Y_VOWN - Y_KOWN) + 6 * 128, kp[12], kp[13], vp[12], vp[13]);
                WG_WAIT(0);
                reg_fence<28>(aq);
                __syncwarp();
                if (lane < 3 && w == 1) mbar_arrive(BAR(B_EMPTY + lane));
                uint32_t qp[14];
#pragma unroll
                for (int i = 0; i < 14; i++) qp[i] = pack2(aq[2 * i], aq[2 * i + 1]);
                stsm4(qo, qp[0], qp[1], qp[2], qp[3]);
                stsm4(qo + 256, qp[4], qp[5], q < 2 ? qp[6] : 0u, q < 2 ? qp[7] : 0u);
                stsm4(qo + 512, q < 2 ? 0u : qp[6], q < 2 ? 0u : qp[7], qp[8], qp[9]);
                stsm4(qo + 768, qp[10], qp[11], qp[12], qp[13]);
                if (!sc) bar_sync(3, 256);
            }
        }
        PROFC(6);
        WAIT(B_KRFULL, 0);
        PROFC(7);
        if (RUN(2)) {
#pragma unroll 1
            for (int hf = sc; hf < 2; hf++) {
                COORDS
                float s[136];
                float na = 0.f, nb = 0.f;
                const float CS = 0.18898223650461361f * 1.4426950408889634f;
                const int kg0 = 8 * hf + 2 * wi;
                const int pmin = 16 - 8 * r - 4 * hf - wi;
                const float NEG = __int_as_float(0xFF800000);
                {
                    uint32_t F[8];
                    const uint32_t qa = sb + OFF_Y + Y_Q + (kg0 + ((lane >> 3) & 1)) * 1024 + (4 * w + (lane >> 4)) * 128 + (lane & 7) * 16;
                    ldsm4(qa, F); ldsm4(qa + 256, F + 4);
                    uint32_t ka = sb + OFF_Y + Y_K + kg0 * 896 + (3 * w + (lane >> 3)) * 128 + (lane & 7) * 16;
#pragma unroll
                    for (int g = 0; g < 34; g++) {
                        uint32_t B[4];
                        if (g >= 12 && g % 4 == 0) ka += __float_as_uint(s[4 * (g - 12)]) & p.zero;
                        ldsm4(ka + g * 896, B);
                        mma16816_first(s + 4 * g, F[0], F[1], F[2], F[3], B[0], B[1]);
                        mma16816_v(s + 4 * g, F[4], F[5], F[6], F[7], B[2], B[3]);
                    }
                    const bool c0 = 2 * q > lr, c1 = 2 * q + 1 > lr;
                    if (!c0) { s[0] = NEG; s[6] = NEG; }
                    if (!c1) { s[1] = NEG; s[7] = NEG; }
                    s[2] = NEG; s[3] = NEG;
                    if (c0) { s[128] = NEG; s[134] = NEG; }
                    if (c1) { s[129] = NEG; s[135] = NEG; }
                    s[132] = NEG; s[133] = NEG;
                    float ma = NEG, mb = NEG;
#pragma unroll
                    for (int pp = 0; pp < 17; pp++) {
                        const float* e = s + 8 * pp;
                        const float bias = pp < pmin ? NEG : 0.f;
                        ma = fmaxf(ma, fmaxf(fmaxf(e[0], e[1]), fmaxf(e[4], e[5])) + bias);
                        mb = fmaxf(mb, fmaxf(fmaxf(e[2], e[3]), fmaxf(e[6], e[7])) + bias);
                    }
                    ma = fmaxf(ma, __shfl_xor_sync(~0u, ma, 1)); mb = fmaxf(mb, __shfl_xor_sync(~0u, mb, 1));
                    ma = fmaxf(ma, __shfl_xor_sync(~0u, ma, 2)); mb = fmaxf(mb, __shfl_xor_sync(~0u, mb, 2));
                    na = -ma * CS; nb = -mb * CS;
                }
                PROFC(8 + 3 * hf);
                {
                    WAIT(B_VRFULL, 0);
                    float o[16] = {}, rs[4] = {};
                    uint32_t pk[2];
                    const uint32_t va = sb + OFF_Y + Y_VR + (kg0 + ((lane >> 3) & 1)) * 896 + (3 * w + (lane >> 4)) * 128 + (lane & 7) * 16;
#pragma unroll
                    for (int pp = 0; pp < 17; pp++) {
                        uint32_t B[8];
                        const uint32_t v = va + pp * 1792 + (pp == 16 || (pp >= 9 && kg0 + 2 * pp >= 32) ? Y_VOWN - 32 * 896 : 0);
                        ldsm4t(v, B); ldsm4t(v + 256, B + 4);
                        float e[8];
                        const float bias = __uint_as_float((pp < pmin ? 0xFF800000u : 0u) | ((pp < 2 ? B[0] : pk[pp & 1]) & p.zero));
#pragma unroll
                        for (int i = 0; i < 8; i++) e[i] = ex2(fmaf(s[8 * pp + i], CS, ((i & 2) ? nb : na) + bias));
                        const uint32_t p0 = pack2(e[0], e[1]), p1 = pack2(e[2], e[3]), p2 = pack2(e[4], e[5]), p3 = pack2(e[6], e[7]);
                        pk[pp & 1] = p3;
                        mma16816(rs, p0, p1, p2, p3, 0x3F803F80u, 0x3F803F80u);
#pragma unroll
                        for (int g = 0; g < 4; g++) mma16816(o + 4 * g, p0, p1, p2, p3, B[2 * g], B[2 * g + 1]);
                    }
                    PROFC(9 + 3 * hf);
                    const float ia = rcp(rs[0]), ib = rcp(rs[2]);
                    uint32_t* og = act + RB_O + hf * 14336 + (7 * j + 3 * w) * 256 + wi * 64 + lane;
#pragma unroll
                    for (int g = 0; g < 4; g++) {
                        if ((g == 3 - 3 * w) ? ((q >> 1) == w) : true) {
                            og[g * 256] = pack2(o[4 * g] * ia, o[4 * g + 1] * ia);
                            og[g * 256 + 32] = pack2(o[4 * g + 2] * ib, o[4 * g + 3] * ib);
                        }
                    }
                    warp_arrive(BAR(B_PUB + 2 + hf));
                    PROFC(10 + 3 * hf);
                }
            }
        }
        uint32_t x1p[14];
        COORDS
        constexpr uint64_t DT = dconst(1024, 128, 0);
        const int tile = opaque((lds1(sb + M_EPOCH) & 1) * 2 + w);
        if (RUN(4)) {
            float ac[28];
            const uint32_t ad = mkdesc(sb + (w ? OFF_Y + HALF : OFF_X), DT), bd = mkdesc(sb + OFF_X + HALF, DB128) + kh;
            WAIT(B_WOFULL, 0);
            WAIT(B_GFULL + w, 0);
            PROFC(28);
            reg_def<28>(ac);
#pragma unroll 1
            for (int u = 0; u < 4; u++) {
                if (u == 2) WAIT(B_XFULL + 2 + w, 1);
                WG_FENCE();
#pragma unroll
                for (int i = 0; i < 7; i++) wgmma_ss_56<DT, DB128>(ac, ad + (7 * u + i) * 128, bd + (7 * u + i) * 128, (u | i) != 0);
            }
            WG_COMMIT();
            WG_WAIT(0);
            reg_fence<28>(ac);
            PROFC(14);
            __syncwarp();
            if (lane < 3) mbar_arrive(BAR(B_EMPTY + 4 - w + lane));
            if (lane < 3 && w == 0) mbar_arrive(BAR(B_EMPTY + lane));
            float ds[4] = {}, da[4] = {}, db[4] = {};
            uint32_t* xo = act + RB_X1 + tile * 14336 + 7 * j * 256 + wi * 64 + lane;
#pragma unroll
            for (int g = 0; g < 7; g++) {
                const float2 ga = *(const float2*)(smem + M_G + (8 * g + 2 * q) * 4);
                x1p[2 * g] = pack2(fmaf(ga.x, ac[4 * g], bf_lo(xr[2 * g])), fmaf(ga.y, ac[4 * g + 1], bf_hi(xr[2 * g])));
                x1p[2 * g + 1] = pack2(fmaf(ga.x, ac[4 * g + 2], bf_lo(xr[2 * g + 1])), fmaf(ga.y, ac[4 * g + 3], bf_hi(xr[2 * g + 1])));
                st_relaxed(xo + g * 256, nz(x1p[2 * g])); st_relaxed(xo + g * 256 + 32, nz(x1p[2 * g + 1]));
                mma1688(ds, x1p[2 * g], x1p[2 * g + 1], 0x3F803F80u);
                mma1688(da, x1p[2 * g], x1p[2 * g + 1], x1p[2 * g]);
                mma1688(db, x1p[2 * g], x1p[2 * g + 1], x1p[2 * g + 1]);
            }
            const int src = (lane & ~3) | (lr >> 1);
            const float qa = __shfl_sync(~0u, (lr & 1) ? da[1] : da[0], src), qb = __shfl_sync(~0u, (lr & 1) ? db[3] : db[2], src);
            const float kk = (q & 1) ? ((q & 2) ? qb : qa) : ((q & 2) ? ds[2] : ds[0]);
            st_relaxed(act + RB_ST + ((tile * 8 + j) * 64 + 16 * wi + lr + 4 * (q & 2)) * 2 + (q & 1), nz(__float_as_uint(kk)));
            __syncwarp();
            if (lane < 2) mbar_arrive(BAR(B_PUB + 4 + w));
        } else reg_def<14>(x1p);
        PROFC(15);
        uint32_t h2a[32], h2b[24];
        {
            const int fa = pass_f(fs, 0), fb = pass_f(fs, 1), fc = pass_f(fs, 2);
            uint32_t* h2g = act + RB_H2 + (8 * w + 2 * wi) * 32 + lane;
            const uint32_t a0 = mkdesc(sb + OFF_Y + w * HALF, DT);
            if (RUN(3)) {
                uint32_t ra2, na2, rb2, nb2;
                {
                    const uint32_t* sg = act + RB_ST + ((tile * 8 + 2 * q) * 64 + 16 * wi + lr) * 2;
                    uint2 u[4];
                    WAIT(B_GFULL + 2 + w, 0);
                    PROFC(16);
#pragma unroll
                    for (int i = 0; i < 4; i++) { const float2 v = lds2f(sb + OFF_X + X_STAT + w * 49152 + ((2 * q + (i >> 1)) * 64 + 16 * wi + lr + 8 * (i & 1)) * 8); u[i] = make_uint2(__float_as_uint(v.x), __float_as_uint(v.y)); }
                    while (__any_sync(~0u, min(min(min(u[0].x, u[0].y), min(u[1].x, u[1].y)), min(min(u[2].x, u[2].y), min(u[3].x, u[3].y))) < 1u - sc)) {
#pragma unroll
                        for (int i = 0; i < 4; i++) u[i] = ld_relaxed2(sg + (i >> 1) * 128 + (i & 1) * 16);
                    }
                    warp_arrive(BAR(B_EMPTY + 3 + 3 * w));
                    float v[4] = {__uint_as_float(u[0].x) + __uint_as_float(u[2].x), __uint_as_float(u[0].y) + __uint_as_float(u[2].y),
                                  __uint_as_float(u[1].x) + __uint_as_float(u[3].x), __uint_as_float(u[1].y) + __uint_as_float(u[3].y)};
#pragma unroll
                    for (int i = 0; i < 4; i++) { v[i] += __shfl_xor_sync(~0u, v[i], 1); v[i] += __shfl_xor_sync(~0u, v[i], 2); }
                    ln_coeffs(v[0] * (1.f / DM), v[1] * (1.f / DM), ra2, na2);
                    ln_coeffs(v[2] * (1.f / DM), v[3] * (1.f / DM), rb2, nb2);
                }
                const uint32_t ha = sb + OFF_Y + w * HALF + (lane >> 4) * 1024 + (2 * wi + ((lane >> 3) & 1)) * 128 + (lane & 7) * 16;
                const uint32_t sta = sb + M_ST + q * 16;
                const uint32_t* xg = act + RB_X1 + tile * 14336 + (lane >> 4) * 256 + wi * 64 + (lane & 15) * 4;
                uint32_t x[8];
                const uint32_t xs = sb + OFF_Y + w * HALF + (lane >> 4) * 1024 + wi * 256 + (lane & 15) * 16;
                uint4 st[2];
                auto load = [&](int s) {
                    if (s == 4) mbar_wait_c(BAR(B_XFULL + 4 + w), 1);
                    ldsm4(ha + s * 4096, x); ldsm4(ha + s * 4096 + 2048, x + 4);
                    st[0] = lds4(sta + s * 128); st[1] = lds4(sta + s * 128 + 64);
                };
                auto prep = [&](int s, uint32_t* f) {
                    if (__any_sync(~0u, min(min(min(x[0], x[1]), min(x[2], x[3])), min(min(x[4], x[5]), min(x[6], x[7]))) < 1u - sc)) {
                        WG_WAIT(0);
                        x1_fix(xg, xs, s);
                        ldsm4(ha + s * 4096, x); ldsm4(ha + s * 4096 + 2048, x + 4);
                    }
#pragma unroll
                    for (int i = 0; i < 2; i++) {
                        f[4 * i] = hfma2(hfma2(x[4 * i], ra2, na2), st[i].x, st[i].y); f[4 * i + 1] = hfma2(hfma2(x[4 * i + 1], rb2, nb2), st[i].x, st[i].y);
                        f[4 * i + 2] = hfma2(hfma2(x[4 * i + 2], ra2, na2), st[i].z, st[i].w); f[4 * i + 3] = hfma2(hfma2(x[4 * i + 3], rb2, nb2), st[i].z, st[i].w);
                    }
                    if (s < 13) load(s + 1);
                    stsm4(ha + s * 4096, f[0], f[1], f[2], f[3]); stsm4(ha + s * 4096 + 2048, f[4], f[5], f[6], f[7]);
                };
                float ac[128];
                uint32_t fr[3][8];
                uint64_t bd = (DB128 & ~0xFFFFFFFFull) | mkdesc(sb, DB128);
                reg_def<128>(ac);
                load(0);
                prep(0, fr[0]);
                PROFC(17);
#pragma unroll
                for (int s = 0; s < 14; s++) {
                    const uint32_t* f = fr[s % 3];
                    WAIT(B_FULL + g1_slot(s), s >= 7);
                    WG_FENCE();
                    wgmma_rl_256(ac, f[0], f[1], f[2], f[3], bd, s != 0);
                    wgmma_rl_256(ac, f[4], f[5], f[6], f[7], bd + 128, 1);
                    bd += s == 6 ? p.zero - 6 * 1024ull : 1024;
                    WG_COMMIT();
                    if (s < 13) prep(s + 1, fr[(s + 1) % 3]);
                    if (s > 0) { WG_WAIT(1); warp_arrive(BAR(B_EMPTY + g1_slot(s - 1))); }
                }
                fence_async_smem();
                PROFC(18);
                WG_WAIT(0);
                reg_fence<128>(ac);
                warp_arrive(BAR(B_EMPTY + 6));
#pragma unroll
                for (int g = 0; g < 16; g++) {
                    h2a[2 * g] = hmul2(pack2_relu(ac[4 * g], ac[4 * g + 1]), pack2(ac[64 + 4 * g], ac[64 + 4 * g + 1]));
                    h2a[2 * g + 1] = hmul2(pack2_relu(ac[4 * g + 2], ac[4 * g + 3]), pack2(ac[64 + 4 * g + 2], ac[64 + 4 * g + 3]));
                }
                bar_sync(1 + w, 128);
            } else reg_def<32>(h2a);
            PROFC(19);
            if (RUN(5)) {
                float ac[64];
                reg_def<64>(ac);
                const uint32_t bx = mkdesc(sb, dconst(8192, 1024, 1));
#pragma unroll kB
                for (int s = 0; s < 7; s++) {
                    WAIT(B_FULL + s, 0);
                    const uint32_t ad = a0 + s * 512, bd = bx + (slot_off(s) >> 4);
                    WG_FENCE();
#pragma unroll
                    for (int k = 0; k < 4; k++) wgmma_ss_128<DT, DB128>(ac, ad + k * 128, bd + k * 128, (s | k) != 0);
                    WG_COMMIT();
                    if (s == 1) {
#pragma unroll
                        for (int g = 0; g < 16; g++) { h2g[(fa / 8 + g) * 512] = h2a[2 * g]; h2g[(fa / 8 + g) * 512 + 32] = h2a[2 * g + 1]; }
                        warp_arrive(BAR(B_PUB + 6));
                    }
                    if (s > 0) { WG_WAIT(1); warp_arrive(BAR(B_EMPTY + s - 1)); }
                }
                WG_WAIT(0);
                reg_fence<64>(ac);
                warp_arrive(BAR(B_EMPTY + 6));
#pragma unroll
                for (int g = 0; g < 8; g++) {
                    h2b[2 * g] = hmul2(pack2_relu(ac[4 * g], ac[4 * g + 1]), pack2(ac[32 + 4 * g], ac[32 + 4 * g + 1]));
                    h2b[2 * g + 1] = hmul2(pack2_relu(ac[4 * g + 2], ac[4 * g + 3]), pack2(ac[32 + 4 * g + 2], ac[32 + 4 * g + 3]));
                }
            } else reg_def<16>(h2b);
            PROFC(27);
            if (RUN(6)) {
                float ac[32];
                reg_def<32>(ac);
                const uint32_t bx = mkdesc(sb, dconst(4096, 512, 2));
#pragma unroll kC
                for (int s = 0; s < 7; s++) {
                    WAIT(B_FULL + s, 1);
                    const uint32_t ad = a0 + s * 512, bd = bx + (slot_off(s) >> 4);
                    WG_FENCE();
#pragma unroll
                    for (int k = 0; k < 4; k++) wgmma_ss_64<DT, dconst(4096, 512, 2)>(ac, ad + k * 128, bd + k * 64, (s | k) != 0);
                    WG_COMMIT();
                    if (s == 1) {
#pragma unroll
                        for (int g = 0; g < 8; g++) { h2g[(fb / 8 + g) * 512] = h2b[2 * g]; h2g[(fb / 8 + g) * 512 + 32] = h2b[2 * g + 1]; }
                        warp_arrive(BAR(B_PUB + 7));
                    }
                    if (s > 0) { WG_WAIT(1); warp_arrive(BAR(B_EMPTY + s - 1)); }
                }
                WG_WAIT(0);
                reg_fence<32>(ac);
                __syncwarp();
                if (lane < 6) mbar_arrive(BAR(B_EMPTY + 6 + lane));
                PROFC(20);
#pragma unroll
                for (int g = 0; g < 4; g++) {
                    h2b[16 + 2 * g] = hmul2(pack2_relu(ac[4 * g], ac[4 * g + 1]), pack2(ac[16 + 4 * g], ac[16 + 4 * g + 1]));
                    h2b[16 + 2 * g + 1] = hmul2(pack2_relu(ac[4 * g + 2], ac[4 * g + 3]), pack2(ac[16 + 4 * g + 2], ac[16 + 4 * g + 3]));
                    h2g[(fc / 8 + g) * 512] = h2b[16 + 2 * g]; h2g[(fc / 8 + g) * 512 + 32] = h2b[16 + 2 * g + 1];
                }
                warp_arrive(BAR(B_PUB + 8));
                asm volatile("barrier.cluster.wait.aligned;" ::: "memory");
                if (lane == 0 && !sc) {
                    uint32_t rb;
                    asm volatile("mapa.shared::cluster.u32 %0, %1, %2;" : "=r"(rb) : "r"(BAR(B_PEER)), "r"(kh ^ 1));
                    asm volatile("mbarrier.arrive.relaxed.cluster.shared::cluster.b64 _, [%0];" ::"r"(rb) : "memory");
                }
            } else reg_def<8>(h2b + 16);
        }
        PROFC(21);
        if (RUN(7)) {
            float ac[56];
            reg_def<56>(ac);
            constexpr uint64_t DAN = dconst(2048, 128, 0);
            constexpr uint64_t DW = dconst(128, 512, 0);
            const uint32_t bx = mkdesc(sb, DW);
#pragma unroll
            for (int e = 0; e < 4; e++) {
                WAIT(B_FULL + e, 0);
                const uint64_t bd = ((DW & ~0xFFFFFFFFull) | bx) + (slot_off(e) >> 4);
                const uint32_t* hh = e < 2 ? h2a + 16 * e : h2b + 16 * (e - 2);
                WG_FENCE();
#pragma unroll
                for (int k = 0; k < (e < 3 ? 4 : 2); k++) wgmma_rl_112(ac, hh[4 * k], hh[4 * k + 1], hh[4 * k + 2], hh[4 * k + 3], bd + (k >> 1) * 512 + (k & 1) * 16, (e | k) != 0);
                WG_COMMIT();
                if (e > 0) { WG_WAIT(1); warp_arrive(BAR(B_EMPTY + e - 1)); }
            }
            PROFC(22);
            uint32_t ad = mkdesc(sb + 4 * 16384 + 8192 + w * 1024, DAN), bd = bx + 4 * 1024, fb_ = BAR(B_FULL + 4), eb_ = BAR(B_EMPTY + 3), par = sc;
#pragma unroll 1
            for (int e = 4; e < 25; e++) {
                mbar_wait_c(fb_, par);
                WG_FENCE();
                wgmma_ss_112<DAN, DW>(ac, ad, bd, 1);
                wgmma_ss_112<DAN, DW>(ac, ad + 256, bd + 16, 1);
                WG_COMMIT();
                WG_WAIT(1);
                warp_arrive(eb_);
                eb_ = fb_ + 8 * (B_EMPTY - B_FULL);
                ad += 1024; bd += 1024; fb_ += 8;
                if (e == 11 || e == 23) { ad -= 12 * 1024; bd -= 12 * 1024; fb_ -= 96; par = (par ^ 1) | sc; }
            }
            mbar_wait_cluster(BAR(B_PEER), sc);
            WG_WAIT(0);
            reg_fence<56>(ac);
            PROFC(24);
            uint32_t rdst, rbar;
            asm volatile("mapa.shared::cluster.u32 %0, %1, %2;" : "=r"(rdst) : "r"(sb + OFF_Y + (5 + w) * 16384 + t * 16), "r"(kh ^ 1 ^ sc));
            asm volatile("mapa.shared::cluster.u32 %0, %1, %2;" : "=r"(rbar) : "r"(BAR(B_XCH + w)), "r"(kh ^ 1 ^ sc));
#pragma unroll
            for (int g = 0; g < 7; g++) {
                const float v0 = ac[28 + 4 * g + 0], v1 = ac[28 + 4 * g + 1];
                const float v2 = ac[28 + 4 * g + 2], v3 = ac[28 + 4 * g + 3];
                if (!sc) asm volatile("st.async.shared::cluster.mbarrier::complete_tx::bytes.v4.f32 [%0], {%1,%2,%3,%4}, [%5];"
                             ::"r"(rdst + g * 2048), "f"(v0), "f"(v1), "f"(v2), "f"(v3), "r"(rbar) : "memory");
            }
            mbar_wait_cluster(BAR(B_XCH + w), sc);
            PROFC(25);
            bf16* og = (sc ? (bf16*)act : p.out + (size_t)128 * r * DM) + (size_t)ra * DM + 56 * j + 2 * q;
#pragma unroll
            for (int g = 0; g < 7; g++) {
                const uint4 rv = *(const uint4*)(smem + OFF_Y + (5 + w) * 16384 + t * 16 + g * 2048);
                const float2 gb = *(const float2*)(smem + M_G + 224 + (8 * g + 2 * q) * 4);
                const float v0 = ac[4 * g + 0] + __uint_as_float(rv.x), v1 = ac[4 * g + 1] + __uint_as_float(rv.y);
                const float v2 = ac[4 * g + 2] + __uint_as_float(rv.z), v3 = ac[4 * g + 3] + __uint_as_float(rv.w);
                *(uint32_t*)(og + 8 * g) = pack2(fmaf(gb.x, v0, bf_lo(x1p[2 * g])), fmaf(gb.y, v1, bf_hi(x1p[2 * g])));
                *(uint32_t*)(og + 8 * DM + 8 * g) = pack2(fmaf(gb.x, v2, bf_lo(x1p[2 * g + 1])), fmaf(gb.y, v3, bf_hi(x1p[2 * g + 1])));
            }
        }
        PROFC(26);
        bar_sync(1 + w, 128);
        if (wi == 0) warp_arrive(BAR(B_DONE));
        return;
    }
    helper_late(p, r, j, warp PROF_ARGS);
}

#undef act
typedef CUresult (*EncodeFn)(CUtensorMap*, CUtensorMapDataType, cuuint32_t, void*, const cuuint64_t*, const cuuint64_t*, const cuuint32_t*,
                             const cuuint32_t*, CUtensorMapInterleave, CUtensorMapSwizzle, CUtensorMapL2promotion, CUtensorMapFloatOOBfill);

static void make_map(EncodeFn fn, CUtensorMap* m, const void* ptr, uint64_t d0, uint64_t d1, uint64_t d2, uint64_t s1, uint64_t s2,
                     uint32_t b0, uint32_t b1, uint32_t b2, CUtensorMapSwizzle sw) {
    cuuint64_t dims[3] = {d0, d1, d2}, strides[2] = {s1, s2};
    cuuint32_t box[3] = {b0, b1, b2}, es[3] = {1, 1, 1};
    CUresult rc = fn(m, CU_TENSOR_MAP_DATA_TYPE_BFLOAT16, 3, (void*)ptr, dims, strides, box, es, CU_TENSOR_MAP_INTERLEAVE_NONE, sw,
                     CU_TENSOR_MAP_L2_PROMOTION_L2_128B, CU_TENSOR_MAP_FLOAT_OOB_FILL_NONE);
    (void)rc;
}

extern "C" void kernel_launch(void* const* d_in, const int* in_sizes, int n_in, void* d_out, int out_size) {
    (void)in_sizes; (void)n_in; (void)out_size;
    static EncodeFn fn = nullptr;
    static uint32_t* act_base = nullptr;
    if (!fn) {
        cudaDriverEntryPointQueryResult st;
        cudaGetDriverEntryPoint("cuTensorMapEncodeTiled", (void**)&fn, cudaEnableDefault, &st);
        void* a = nullptr;
        cudaGetSymbolAddress(&a, g_act);
        act_base = (uint32_t*)(((uintptr_t)a + 0xFFFFF) & ~(uintptr_t)0xFFFFF);
        cudaFuncSetAttribute(fused_block_kernel, cudaFuncAttributeMaxDynamicSharedMemorySize, SMEM_BYTES);
    }
    Params p;
    p.x = (const bf16*)d_in[0];
    const bf16* wqkv = (const bf16*)d_in[1];
    p.wqkv = wqkv;
    p.wop = (const bf16*)d_in[2];
    p.wg = (const bf16*)d_in[4];
    p.wu = (const bf16*)d_in[5];
    p.wd = (const bf16*)d_in[6];
    p.c = (const bf16*)d_in[7];
    p.wmod = (const bf16*)d_in[8];
    p.out = (bf16*)d_out;
    p.zero = 0;
    p.actb = act_base;
    make_map(fn, &p.wm, p.wmod, 2688, 448, 1, 5376, 5376 * 448, 16, 224, 1, CU_TENSOR_MAP_SWIZZLE_NONE);
    make_map(fn, &p.xm, p.x, 448, 2048, 1, 896, 896 * 2048, 64, 128, 1, CU_TENSOR_MAP_SWIZZLE_128B);
    make_map(fn, &p.qkv, wqkv, 1344, 448, 1, 2688, 2688 * 448, 64, 224, 1, CU_TENSOR_MAP_SWIZZLE_128B);
    make_map(fn, &p.wo, p.wop, 448, 448, 1, 896, 896 * 448, 64, 224, 1, CU_TENSOR_MAP_SWIZZLE_128B);
    make_map(fn, &p.ga, p.wg, 64, 448, 28, 3584, 128, 64, 32, 2, CU_TENSOR_MAP_SWIZZLE_128B);
    make_map(fn, &p.ua, p.wu, 64, 448, 28, 3584, 128, 64, 32, 2, CU_TENSOR_MAP_SWIZZLE_128B);
    make_map(fn, &p.gb, p.wg, 64, 448, 28, 3584, 128, 64, 64, 1, CU_TENSOR_MAP_SWIZZLE_128B);
    make_map(fn, &p.ub, p.wu, 64, 448, 28, 3584, 128, 64, 64, 1, CU_TENSOR_MAP_SWIZZLE_128B);
    make_map(fn, &p.gc, p.wg, 32, 448, 56, 3584, 64, 32, 64, 1, CU_TENSOR_MAP_SWIZZLE_64B);
    make_map(fn, &p.uc, p.wu, 32, 448, 56, 3584, 64, 32, 64, 1, CU_TENSOR_MAP_SWIZZLE_64B);
    make_map(fn, &p.dn, p.wd, 8, 1792, 56, 896, 16, 8, 32, 7, CU_TENSOR_MAP_SWIZZLE_NONE);
    fused_block_kernel<<<GRID, 384, SMEM_BYTES>>>(p);
}
```

```cpp
#include <cuda_runtime.h>
#include <cuda_bf16.h>
#include <cuda.h>
#include <stdint.h>

typedef __nv_bfloat16 bf16;

__device__ __forceinline__ void wgmma_rl_56(float* d, uint32_t a0, uint32_t a1, uint32_t a2, uint32_t a3, uint64_t db, int sd) {
  asm volatile("{\n.reg .pred p;\nsetp.ne.b32 p, %33, 0;\n"
    "wgmma.mma_async.sync.aligned.m64n56k16.f32.bf16.bf16 {%0,%1,%2,%3,%4,%5,%6,%7,%8,%9,%10,%11,%12,%13,%14,%15,%16,%17,%18,%19,%20,%21,%22,%23,%24,%25,%26,%27}, {%28,%29,%30,%31}, %32, p, 1, 1, 1;\n}\n"
    : "+f"(d[0]),"+f"(d[1]),"+f"(d[2]),"+f"(d[3]),"+f"(d[4]),"+f"(d[5]),"+f"(d[6]),"+f"(d[7]),"+f"(d[8]),"+f"(d[9]),"+f"(d[10]),"+f"(d[11]),"+f"(d[12]),"+f"(d[13]),"+f"(d[14]),"+f"(d[15]),"+f"(d[16]),"+f"(d[17]),"+f"(d[18]),"+f"(d[19]),"+f"(d[20]),"+f"(d[21]),"+f"(d[22]),"+f"(d[23]),"+f"(d[24]),"+f"(d[25]),"+f"(d[26]),"+f"(d[27])
    : "r"(a0), "r"(a1), "r"(a2), "r"(a3), "l"(db), "r"(sd));
}
template<uint64_t CA, uint64_t CB> __device__ __forceinline__ void wgmma_ss_56(float* d, uint32_t da, uint32_t db, int sd) {
  asm volatile("{\n.reg .pred p;\n.reg .b64 a, b;\nsetp.ne.b32 p, %30, 0;\nmov.b64 a, {%28, %31};\nmov.b64 b, {%29, %32};\n"
    "wgmma.mma_async.sync.aligned.m64n56k16.f32.bf16.bf16 {%0,%1,%2,%3,%4,%5,%6,%7,%8,%9,%10,%11,%12,%13,%14,%15,%16,%17,%18,%19,%20,%21,%22,%23,%24,%25,%26,%27}, a, b, p, 1, 1, 0, 1;\n}\n"
    : "+f"(d[0]),"+f"(d[1]),"+f"(d[2]),"+f"(d[3]),"+f"(d[4]),"+f"(d[5]),"+f"(d[6]),"+f"(d[7]),"+f"(d[8]),"+f"(d[9]),"+f"(d[10]),"+f"(d[11]),"+f"(d[12]),"+f"(d[13]),"+f"(d[14]),"+f"(d[15]),"+f"(d[16]),"+f"(d[17]),"+f"(d[18]),"+f"(d[19]),"+f"(d[20]),"+f"(d[21]),"+f"(d[22]),"+f"(d[23]),"+f"(d[24]),"+f"(d[25]),"+f"(d[26]),"+f"(d[27])
    : "r"(da), "r"(db), "r"(sd), "n"((uint32_t)(CA >> 32)), "n"((uint32_t)(CB >> 32)));
}
__device__ __forceinline__ void wgmma_rl_256(float* d, uint32_t a0, uint32_t a1, uint32_t a2, uint32_t a3, uint64_t db, int sd) {
  asm volatile("{\n.reg .pred p;\nsetp.ne.b32 p, %133, 0;\n"
    "wgmma.mma_async.sync.aligned.m64n256k16.f32.bf16.bf16 {%0,%1,%2,%3,%4,%5,%6,%7,%8,%9,%10,%11,%12,%13,%14,%15,%16,%17,%18,%19,%20,%21,%22,%23,%24,%25,%26,%27,%28,%29,%30,%31,%32,%33,%34,%35,%36,%37,%38,%39,%40,%41,%42,%43,%44,%45,%46,%47,%48,%49,%50,%51,%52,%53,%54,%55,%56,%57,%58,%59,%60,%61,%62,%63,%64,%65,%66,%67,%68,%69,%70,%71,%72,%73,%74,%75,%76,%77,%78,%79,%80,%81,%82,%83,%84,%85,%86,%87,%88,%89,%90,%91,%92,%93,%94,%95,%96,%97,%98,%99,%100,%101,%102,%103,%104,%105,%106,%107,%108,%109,%110,%111,%112,%113,%114,%115,%116,%117,%118,%119,%120,%121,%122,%123,%124,%125,%126,%127}, {%128,%129,%130,%131}, %132, p, 1, 1, 1;\n}\n"
    : "+f"(d[0]),"+f"(d[1]),"+f"(d[2]),"+f"(d[3]),"+f"(d[4]),"+f"(d[5]),"+f"(d[6]),"+f"(d[7]),"+f"(d[8]),"+f"(d[9]),"+f"(d[10]),"+f"(d[11]),"+f"(d[12]),"+f"(d[13]),"+f"(d[14]),"+f"(d[15]),"+f"(d[16]),"+f"(d[17]),"+f"(d[18]),"+f"(d[19]),"+f"(d[20]),"+f"(d[21]),"+f"(d[22]),"+f"(d[23]),"+f"(d[24]),"+f"(d[25]),"+f"(d[26]),"+f"(d[27]),"+f"(d[28]),"+f"(d[29]),"+f"(d[30]),"+f"(d[31]),"+f"(d[32]),"+f"(d[33]),"+f"(d[34]),"+f"(d[35]),"+f"(d[36]),"+f"(d[37]),"+f"(d[38]),"+f"(d[39]),"+f"(d[40]),"+f"(d[41]),"+f"(d[42]),"+f"(d[43]),"+f"(d[44]),"+f"(d[45]),"+f"(d[46]),"+f"(d[47]),"+f"(d[48]),"+f"(d[49]),"+f"(d[50]),"+f"(d[51]),"+f"(d[52]),"+f"(d[53]),"+f"(d[54]),"+f"(d[55]),"+f"(d[56]),"+f"(d[57]),"+f"(d[58]),"+f"(d[59]),"+f"(d[60]),"+f"(d[61]),"+f"(d[62]),"+f"(d[63]),"+f"(d[64]),"+f"(d[65]),"+f"(d[66]),"+f"(d[67]),"+f"(d[68]),"+f"(d[69]),"+f"(d[70]),"+f"(d[71]),"+f"(d[72]),"+f"(d[73]),"+f"(d[74]),"+f"(d[75]),"+f"(d[76]),"+f"(d[77]),"+f"(d[78]),"+f"(d[79]),"+f"(d[80]),"+f"(d[81]),"+f"(d[82]),"+f"(d[83]),"+f"(d[84]),"+f"(d[85]),"+f"(d[86]),"+f"(d[87]),"+f"(d[88]),"+f"(d[89]),"+f"(d[90]),"+f"(d[91]),"+f"(d[92]),"+f"(d[93]),"+f"(d[94]),"+f"(d[95]),"+f"(d[96]),"+f"(d[97]),"+f"(d[98]),"+f"(d[99]),"+f"(d[100]),"+f"(d[101]),"+f"(d[102]),"+f"(d[103]),"+f"(d[104]),"+f"(d[105]),"+f"(d[106]),"+f"(d[107]),"+f"(d[108]),"+f"(d[109]),"+f"(d[110]),"+f"(d[111]),"+f"(d[112]),"+f"(d[113]),"+f"(d[114]),"+f"(d[115]),"+f"(d[116]),"+f"(d[117]),"+f"(d[118]),"+f"(d[119]),"+f"(d[120]),"+f"(d[121]),"+f"(d[122]),"+f"(d[123]),"+f"(d[124]),"+f"(d[125]),"+f"(d[126]),"+f"(d[127])
    : "r"(a0), "r"(a1), "r"(a2), "r"(a3), "l"(db), "r"(sd));
}
template<uint64_t CA, uint64_t CB> __device__ __forceinline__ void wgmma_ss_128(float* d, uint32_t da, uint32_t db, int sd) {
  asm volatile("{\n.reg .pred p;\n.reg .b64 a, b;\nsetp.ne.b32 p, %66, 0;\nmov.b64 a, {%64, %67};\nmov.b64 b, {%65, %68};\n"
    "wgmma.mma_async.sync.aligned.m64n128k16.f32.bf16.bf16 {%0,%1,%2,%3,%4,%5,%6,%7,%8,%9,%10,%11,%12,%13,%14,%15,%16,%17,%18,%19,%20,%21,%22,%23,%24,%25,%26,%27,%28,%29,%30,%31,%32,%33,%34,%35,%36,%37,%38,%39,%40,%41,%42,%43,%44,%45,%46,%47,%48,%49,%50,%51,%52,%53,%54,%55,%56,%57,%58,%59,%60,%61,%62,%63}, a, b, p, 1, 1, 0, 1;\n}\n"
    : "+f"(d[0]),"+f"(d[1]),"+f"(d[2]),"+f"(d[3]),"+f"(d[4]),"+f"(d[5]),"+f"(d[6]),"+f"(d[7]),"+f"(d[8]),"+f"(d[9]),"+f"(d[10]),"+f"(d[11]),"+f"(d[12]),"+f"(d[13]),"+f"(d[14]),"+f"(d[15]),"+f"(d[16]),"+f"(d[17]),"+f"(d[18]),"+f"(d[19]),"+f"(d[20]),"+f"(d[21]),"+f"(d[22]),"+f"(d[23]),"+f"(d[24]),"+f"(d[25]),"+f"(d[26]),"+f"(d[27]),"+f"(d[28]),"+f"(d[29]),"+f"(d[30]),"+f"(d[31]),"+f"(d[32]),"+f"(d[33]),"+f"(d[34]),"+f"(d[35]),"+f"(d[36]),"+f"(d[37]),"+f"(d[38]),"+f"(d[39]),"+f"(d[40]),"+f"(d[41]),"+f"(d[42]),"+f"(d[43]),"+f"(d[44]),"+f"(d[45]),"+f"(d[46]),"+f"(d[47]),"+f"(d[48]),"+f"(d[49]),"+f"(d[50]),"+f"(d[51]),"+f"(d[52]),"+f"(d[53]),"+f"(d[54]),"+f"(d[55]),"+f"(d[56]),"+f"(d[57]),"+f"(d[58]),"+f"(d[59]),"+f"(d[60]),"+f"(d[61]),"+f"(d[62]),"+f"(d[63])
    : "r"(da), "r"(db), "r"(sd), "n"((uint32_t)(CA >> 32)), "n"((uint32_t)(CB >> 32)));
}
template<uint64_t CA, uint64_t CB> __device__ __forceinline__ void wgmma_ss_64(float* d, uint32_t da, uint32_t db, int sd) {
  asm volatile("{\n.reg .pred p;\n.reg .b64 a, b;\nsetp.ne.b32 p, %34, 0;\nmov.b64 a, {%32, %35};\nmov.b64 b, {%33, %36};\n"
    "wgmma.mma_async.sync.aligned.m64n64k16.f32.bf16.bf16 {%0,%1,%2,%3,%4,%5,%6,%7,%8,%9,%10,%11,%12,%13,%14,%15,%16,%17,%18,%19,%20,%21,%22,%23,%24,%25,%26,%27,%28,%29,%30,%31}, a, b, p, 1, 1, 0, 1;\n}\n"
    : "+f"(d[0]),"+f"(d[1]),"+f"(d[2]),"+f"(d[3]),"+f"(d[4]),"+f"(d[5]),"+f"(d[6]),"+f"(d[7]),"+f"(d[8]),"+f"(d[9]),"+f"(d[10]),"+f"(d[11]),"+f"(d[12]),"+f"(d[13]),"+f"(d[14]),"+f"(d[15]),"+f"(d[16]),"+f"(d[17]),"+f"(d[18]),"+f"(d[19]),"+f"(d[20]),"+f"(d[21]),"+f"(d[22]),"+f"(d[23]),"+f"(d[24]),"+f"(d[25]),"+f"(d[26]),"+f"(d[27]),"+f"(d[28]),"+f"(d[29]),"+f"(d[30]),"+f"(d[31])
    : "r"(da), "r"(db), "r"(sd), "n"((uint32_t)(CA >> 32)), "n"((uint32_t)(CB >> 32)));
}
template<uint64_t CA, uint64_t CB> __device__ __forceinline__ void wgmma_ss_112(float* d, uint32_t da, uint32_t db, int sd) {
  asm volatile("{\n.reg .pred p;\n.reg .b64 a, b;\nsetp.ne.b32 p, %58, 0;\nmov.b64 a, {%56, %59};\nmov.b64 b, {%57, %60};\n"
    "wgmma.mma_async.sync.aligned.m64n112k16.f32.bf16.bf16 {%0,%1,%2,%3,%4,%5,%6,%7,%8,%9,%10,%11,%12,%13,%14,%15,%16,%17,%18,%19,%20,%21,%22,%23,%24,%25,%26,%27,%28,%29,%30,%31,%32,%33,%34,%35,%36,%37,%38,%39,%40,%41,%42,%43,%44,%45,%46,%47,%48,%49,%50,%51,%52,%53,%54,%55}, a, b, p, 1, 1, 0, 1;\n}\n"
    : "+f"(d[0]),"+f"(d[1]),"+f"(d[2]),"+f"(d[3]),"+f"(d[4]),"+f"(d[5]),"+f"(d[6]),"+f"(d[7]),"+f"(d[8]),"+f"(d[9]),"+f"(d[10]),"+f"(d[11]),"+f"(d[12]),"+f"(d[13]),"+f"(d[14]),"+f"(d[15]),"+f"(d[16]),"+f"(d[17]),"+f"(d[18]),"+f"(d[19]),"+f"(d[20]),"+f"(d[21]),"+f"(d[22]),"+f"(d[23]),"+f"(d[24]),"+f"(d[25]),"+f"(d[26]),"+f"(d[27]),"+f"(d[28]),"+f"(d[29]),"+f"(d[30]),"+f"(d[31]),"+f"(d[32]),"+f"(d[33]),"+f"(d[34]),"+f"(d[35]),"+f"(d[36]),"+f"(d[37]),"+f"(d[38]),"+f"(d[39]),"+f"(d[40]),"+f"(d[41]),"+f"(d[42]),"+f"(d[43]),"+f"(d[44]),"+f"(d[45]),"+f"(d[46]),"+f"(d[47]),"+f"(d[48]),"+f"(d[49]),"+f"(d[50]),"+f"(d[51]),"+f"(d[52]),"+f"(d[53]),"+f"(d[54]),"+f"(d[55])
    : "r"(da), "r"(db), "r"(sd), "n"((uint32_t)(CA >> 32)), "n"((uint32_t)(CB >> 32)));
}
__device__ __forceinline__ void wgmma_rl_112(float* d, uint32_t a0, uint32_t a1, uint32_t a2, uint32_t a3, uint64_t db, int sd) {
  asm volatile("{\n.reg .pred p;\nsetp.ne.b32 p, %61, 0;\n"
    "wgmma.mma_async.sync.aligned.m64n112k16.f32.bf16.bf16 {%0,%1,%2,%3,%4,%5,%6,%7,%8,%9,%10,%11,%12,%13,%14,%15,%16,%17,%18,%19,%20,%21,%22,%23,%24,%25,%26,%27,%28,%29,%30,%31,%32,%33,%34,%35,%36,%37,%38,%39,%40,%41,%42,%43,%44,%45,%46,%47,%48,%49,%50,%51,%52,%53,%54,%55}, {%56,%57,%58,%59}, %60, p, 1, 1, 1;\n}\n"
    : "+f"(d[0]),"+f"(d[1]),"+f"(d[2]),"+f"(d[3]),"+f"(d[4]),"+f"(d[5]),"+f"(d[6]),"+f"(d[7]),"+f"(d[8]),"+f"(d[9]),"+f"(d[10]),"+f"(d[11]),"+f"(d[12]),"+f"(d[13]),"+f"(d[14]),"+f"(d[15]),"+f"(d[16]),"+f"(d[17]),"+f"(d[18]),"+f"(d[19]),"+f"(d[20]),"+f"(d[21]),"+f"(d[22]),"+f"(d[23]),"+f"(d[24]),"+f"(d[25]),"+f"(d[26]),"+f"(d[27]),"+f"(d[28]),"+f"(d[29]),"+f"(d[30]),"+f"(d[31]),"+f"(d[32]),"+f"(d[33]),"+f"(d[34]),"+f"(d[35]),"+f"(d[36]),"+f"(d[37]),"+f"(d[38]),"+f"(d[39]),"+f"(d[40]),"+f"(d[41]),"+f"(d[42]),"+f"(d[43]),"+f"(d[44]),"+f"(d[45]),"+f"(d[46]),"+f"(d[47]),"+f"(d[48]),"+f"(d[49]),"+f"(d[50]),"+f"(d[51]),"+f"(d[52]),"+f"(d[53]),"+f"(d[54]),"+f"(d[55])
    : "r"(a0), "r"(a1), "r"(a2), "r"(a3), "l"(db), "r"(sd));
}

constexpr int DM = 448;
constexpr int NCTA = 128;
#define MAPPING 1
#define GRID 128
#define PINGPONG 0
#define WIN 6
#define WIN_END 25
#define UNR_B 1
#define UNR_C 1
constexpr int kB = UNR_B, kC = UNR_C;
#define LIKELY(x) __builtin_expect(!!(x), 1)
#define PACE 1
#define PACE_END 6
#define GEMV_AT 2
#define NPRE 14
#define MAP_S 4
constexpr int SPIN_LIMIT = 1 << 22;

constexpr uint32_t OFF_X = 0, OFF_Y = 114688, OFF_MISC = 229376, SMEM_BYTES = 232448;
constexpr uint32_t Y_VR = 0, Y_K = 28672, Y_KOWN = 57344, Y_VOWN = 71680, Y_Q = 86016;
constexpr uint32_t HALF = 57344;
constexpr uint32_t X_STAT = 49152;
constexpr uint32_t M_BAR = OFF_MISC;
constexpr uint32_t M_ST = OFF_MISC + 512;
constexpr uint32_t M_G = OFF_MISC + 2304;
constexpr uint32_t M_EPOCH = OFF_MISC + 3040;
enum { B_XFULL = 0, B_FULLK = 7, B_FULLV = 8, B_FULLQ, B_KRFULL, B_VRFULL, B_WOFULL, B_XCH, B_MOD1 = 15, B_FULL = 16, B_WMFULL = 30,
       B_EMPTY = 32, B_XFREE = B_EMPTY + 12, B_GEMV, B_PEER,
       B_PUB = 47,
       B_WMFREE = 56, B_HRDY, B_GFULL = B_HRDY + 3, B_DONE = 31, B_DUMMY = B_GEMV };

__device__ uint32_t g_ticket;
__device__ __align__(128) uint32_t g_mod[8 * 6 * DM];
__device__ __align__(128) uint32_t g_flag[144 * 128];
constexpr int RB_WORDS = 262144, RB_KV = 0, RB_O = 57344, RB_X1 = 86016, RB_H2 = 143360, RB_ST = 258048;
__device__ __align__(128) uint32_t g_act[18 * RB_WORDS];
__device__ __align__(128) uint32_t g_wd[56 * 4 * 1792];
#define PROFH(id)
#define PROFH1(id)
#define PROFC(id)

struct alignas(64) Params {
    CUtensorMap wm, xm, qkv, wo, ga, ua, gb, ub, gc, uc, dn;
    const bf16 *x, *c, *wqkv, *wmod, *wg, *wu, *wd, *wop;
    bf16* out;
    uint32_t* actb;
    uint32_t zero;
};

__device__ __forceinline__ void mbar_init(uint32_t bar, int cnt) { asm volatile("mbarrier.init.shared::cta.b64 [%0], %1;" ::"r"(bar), "r"(cnt) : "memory"); }
__device__ __forceinline__ void mbar_expect_tx(uint32_t bar, uint32_t bytes) { asm volatile("mbarrier.arrive.expect_tx.shared::cta.b64 _, [%0], %1;" ::"r"(bar), "r"(bytes) : "memory"); }
__device__ __forceinline__ void mbar_arrive(uint32_t bar) { asm volatile("mbarrier.arrive.shared::cta.b64 _, [%0];" ::"r"(bar) : "memory"); }
__device__ __forceinline__ void mbar_wait(uint32_t bar, uint32_t parity) {
    uint32_t ok; int n = 0;
    do {
        asm volatile("{\n.reg .pred p;\nmbarrier.try_wait.parity.shared::cta.b64 p, [%1], %2;\nselp.u32 %0, 1, 0, p;\n}" : "=r"(ok) : "r"(bar), "r"(parity) : "memory");
        if (++n > SPIN_LIMIT) __trap();
    } while (!ok);
}
__device__ __forceinline__ void mbar_wait_c(uint32_t bar, uint32_t parity) {
    asm volatile("{\n.reg .pred p;\nWL:\nmbarrier.try_wait.parity.shared::cta.b64 p, [%0], %1, 0x989680;\n@!p bra WL;\n}" ::"r"(bar), "r"(parity) : "memory");
}
__device__ __forceinline__ void mbar_wait_cluster(uint32_t bar, uint32_t parity) {
    asm volatile("{\n.reg .pred p;\nWL:\nmbarrier.try_wait.parity.acquire.cluster.shared::cta.b64 p, [%0], %1, 0x989680;\n@!p bra WL;\n}" ::"r"(bar), "r"(parity) : "memory");
}
__device__ __forceinline__ void warp_arrive(uint32_t bar) {
    __syncwarp();
    asm volatile("{\n.reg .pred p;\nelect.sync _|p, 0xffffffff;\n@p mbarrier.arrive.shared::cta.b64 _, [%0];\n}" ::"r"(bar) : "memory");
}
__device__ __forceinline__ int opaque(int v) { return __shfl_sync(~0u, v, 0); }
__device__ __forceinline__ int fresh_tid() { int v; asm volatile("mov.u32 %0, %%tid.x;" : "=r"(v)); return v; }
__device__ __forceinline__ void bar_sync(int id, int n) { asm volatile("bar.sync %0, %1;" ::"r"(id), "r"(n) : "memory"); }
__device__ __forceinline__ void bar_arrive(int id, int n) { asm volatile("bar.arrive %0, %1;" ::"r"(id), "r"(n) : "memory"); }
__device__ __forceinline__ void fence_async_smem() { asm volatile("fence.proxy.async.shared::cta;" ::: "memory"); }
__device__ __forceinline__ void fence_async_global() { asm volatile("fence.proxy.async.global;" ::: "memory"); }
__device__ __forceinline__ void fence_gpu() { asm volatile("fence.release.gpu;" ::: "memory"); }
__device__ __forceinline__ void tma3(uint32_t dst, const CUtensorMap* m, int c0, int c1, int c2, uint32_t bar) {
    asm volatile("cp.async.bulk.tensor.3d.shared::cluster.global.mbarrier::complete_tx::bytes [%0], [%1, {%3, %4, %5}], [%2];"
                 ::"r"(dst), "l"(m), "r"(bar), "r"(c0), "r"(c1), "r"(c2) : "memory");
}
__device__ __forceinline__ void bulk_load(uint32_t dst, const void* src, uint32_t bytes, uint32_t bar) {
    asm volatile("cp.async.bulk.shared::cluster.global.mbarrier::complete_tx::bytes [%0], [%1], %2, [%3];" ::"r"(dst), "l"(src), "r"(bytes), "r"(bar) : "memory");
}
__device__ __forceinline__ void expect_e(uint32_t bar, uint32_t bytes) {
    asm volatile("{\n.reg .pred p;\nelect.sync _|p, 0xffffffff;\n@p mbarrier.arrive.expect_tx.shared::cta.b64 _, [%0], %1;\n}" ::"r"(bar), "r"(bytes) : "memory");
}
__device__ __forceinline__ void tma3_e(uint32_t dst, const CUtensorMap* m, int c0, int c1, int c2, uint32_t bar) {
    asm volatile("{\n.reg .pred p;\nelect.sync _|p, 0xffffffff;\n@p cp.async.bulk.tensor.3d.shared::cluster.global.mbarrier::complete_tx::bytes [%0], [%1, {%3, %4, %5}], [%2];\n}"
                 ::"r"(dst), "l"(m), "r"(bar), "r"(c0), "r"(c1), "r"(c2) : "memory");
}
__device__ __forceinline__ void bulk_e(uint32_t dst, const void* src, uint32_t bytes, uint32_t bar) {
    asm volatile("{\n.reg .pred p;\nelect.sync _|p, 0xffffffff;\n@p cp.async.bulk.shared::cluster.global.mbarrier::complete_tx::bytes [%0], [%1], %2, [%3];\n}"
                 ::"r"(dst), "l"(src), "r"(bytes), "r"(bar) : "memory");
}
__device__ __forceinline__ void init_e(uint32_t bar, int cnt) {
    asm volatile("{\n.reg .pred p;\nelect.sync _|p, 0xffffffff;\n@p mbarrier.init.shared::cta.b64 [%0], %1;\n}" ::"r"(bar), "r"(cnt) : "memory");
}
__device__ __forceinline__ void l2_prefetch_e(const void* src, uint32_t bytes) {
    asm volatile("{\n.reg .pred p;\nelect.sync _|p, 0xffffffff;\n@p cp.async.bulk.prefetch.L2.global [%0], %1;\n}" ::"l"(src), "r"(bytes) : "memory");
}
__device__ __forceinline__ uint32_t ld_relaxed(const uint32_t* p) { uint32_t v; asm volatile("ld.relaxed.gpu.global.u32 %0, [%1];" : "=r"(v) : "l"(p) : "memory"); return v; }
__device__ __forceinline__ void st_relaxed(uint32_t* p, uint32_t v) { asm volatile("st.relaxed.gpu.global.u32 [%0], %1;" ::"l"(p), "r"(v) : "memory"); }
__device__ __forceinline__ uint4 ld_relaxed4(const uint4* p) { uint4 v; asm volatile("ld.relaxed.gpu.global.v4.u32 {%0,%1,%2,%3}, [%4];" : "=r"(v.x), "=r"(v.y), "=r"(v.z), "=r"(v.w) : "l"(p) : "memory"); return v; }
__device__ __forceinline__ void st_relaxed4(uint4* p, uint4 v) { asm volatile("st.relaxed.gpu.global.v4.u32 [%0], {%1,%2,%3,%4};" ::"l"(p), "r"(v.x), "r"(v.y), "r"(v.z), "r"(v.w) : "memory"); }
__device__ __forceinline__ uint4 ldg_nc4(const void* p) { uint4 v; asm volatile("ld.global.nc.L1::no_allocate.v4.u32 {%0,%1,%2,%3}, [%4];" : "=r"(v.x), "=r"(v.y), "=r"(v.z), "=r"(v.w) : "l"(p)); return v; }
__device__ __forceinline__ uint32_t ldg_nc(const void* p) { uint32_t v; asm volatile("ld.global.nc.u32 %0, [%1];" : "=r"(v) : "l"(p)); return v; }
__device__ __forceinline__ uint32_t ld_acquire(const uint32_t* p) { uint32_t v; asm volatile("ld.acquire.gpu.global.u32 %0, [%1];" : "=r"(v) : "l"(p) : "memory"); return v; }
__device__ __forceinline__ uint4 lds4(uint32_t a) { uint4 v; asm volatile("ld.shared.v4.u32 {%0,%1,%2,%3}, [%4];" : "=r"(v.x), "=r"(v.y), "=r"(v.z), "=r"(v.w) : "r"(a) : "memory"); return v; }
__device__ __forceinline__ float2 lds2f(uint32_t a) { float2 v; asm volatile("ld.shared.v2.f32 {%0,%1}, [%2];" : "=f"(v.x), "=f"(v.y) : "r"(a) : "memory"); return v; }
__device__ __forceinline__ uint32_t lds1(uint32_t a) { uint32_t v; asm volatile("ld.shared.u32 %0, [%1];" : "=r"(v) : "r"(a) : "memory"); return v; }
__device__ __forceinline__ void sts4(uint32_t a, uint4 v) { asm volatile("st.shared.v4.u32 [%0], {%1,%2,%3,%4};" ::"r"(a), "r"(v.x), "r"(v.y), "r"(v.z), "r"(v.w) : "memory"); }
__device__ __forceinline__ void sts2(uint32_t a, uint32_t x, uint32_t y) { asm volatile("st.shared.v2.u32 [%0], {%1,%2};" ::"r"(a), "r"(x), "r"(y) : "memory"); }
__device__ __forceinline__ void sts1(uint32_t a, uint32_t v) { asm volatile("st.shared.u32 [%0], %1;" ::"r"(a), "r"(v) : "memory"); }
__device__ __forceinline__ void stsm4(uint32_t a, uint32_t r0, uint32_t r1, uint32_t r2, uint32_t r3) {
    asm volatile("stmatrix.sync.aligned.m8n8.x4.shared.b16 [%0], {%1,%2,%3,%4};" ::"r"(a), "r"(r0), "r"(r1), "r"(r2), "r"(r3));
}
__device__ __forceinline__ uint32_t pack2(float lo, float hi) { uint32_t r; asm("cvt.rn.bf16x2.f32 %0, %1, %2;" : "=r"(r) : "f"(hi), "f"(lo)); return r; }
__device__ __forceinline__ uint32_t pack2_relu(float lo, float hi) { uint32_t r; asm("cvt.rn.relu.bf16x2.f32 %0, %1, %2;" : "=r"(r) : "f"(hi), "f"(lo)); return r; }
__device__ __forceinline__ uint32_t hfma2(uint32_t a, uint32_t b, uint32_t c) { uint32_t r; asm("fma.rn.bf16x2 %0, %1, %2, %3;" : "=r"(r) : "r"(a), "r"(b), "r"(c)); return r; }
__device__ __forceinline__ uint32_t hmul2(uint32_t a, uint32_t b) { uint32_t r; asm("mul.rn.bf16x2 %0, %1, %2;" : "=r"(r) : "r"(a), "r"(b)); return r; }
__device__ __forceinline__ float bf_lo(uint32_t v) { return __uint_as_float(v << 16); }
__device__ __forceinline__ float bf_hi(uint32_t v) { return __uint_as_float(v & 0xFFFF0000u); }
__device__ __forceinline__ float bf_round(float v) { return bf_lo(pack2(v, 0.f)); }
__device__ __forceinline__ float ex2(float x) { float r; asm("ex2.approx.ftz.f32 %0, %1;" : "=f"(r) : "f"(x)); return r; }
__device__ __forceinline__ void mma16816(float* d, uint32_t a0, uint32_t a1, uint32_t a2, uint32_t a3, uint32_t b0, uint32_t b1) {
    asm("mma.sync.aligned.m16n8k16.row.col.f32.bf16.bf16.f32 {%0,%1,%2,%3}, {%4,%5,%6,%7}, {%8,%9}, {%0,%1,%2,%3};"
        : "+f"(d[0]), "+f"(d[1]), "+f"(d[2]), "+f"(d[3]) : "r"(a0), "r"(a1), "r"(a2), "r"(a3), "r"(b0), "r"(b1));
}
__device__ __forceinline__ void mma16816_first(float* d, uint32_t a0, uint32_t a1, uint32_t a2, uint32_t a3, uint32_t b0, uint32_t b1) {
    asm volatile("mma.sync.aligned.m16n8k16.row.col.f32.bf16.bf16.f32 {%0,%1,%2,%3}, {%4,%5,%6,%7}, {%8,%9}, {%10,%10,%10,%10};"
        : "=f"(d[0]), "=f"(d[1]), "=f"(d[2]), "=f"(d[3]) : "r"(a0), "r"(a1), "r"(a2), "r"(a3), "r"(b0), "r"(b1), "f"(0.f));
}
__device__ __forceinline__ void mma16816_v(float* d, uint32_t a0, uint32_t a1, uint32_t a2, uint32_t a3, uint32_t b0, uint32_t b1) {
    asm volatile("mma.sync.aligned.m16n8k16.row.col.f32.bf16.bf16.f32 {%0,%1,%2,%3}, {%4,%5,%6,%7}, {%8,%9}, {%0,%1,%2,%3};"
        : "+f"(d[0]), "+f"(d[1]), "+f"(d[2]), "+f"(d[3]) : "r"(a0), "r"(a1), "r"(a2), "r"(a3), "r"(b0), "r"(b1));
}
__device__ __forceinline__ void mma1688(float* d, uint32_t a0, uint32_t a1, uint32_t b0) {
    asm("mma.sync.aligned.m16n8k8.row.col.f32.bf16.bf16.f32 {%0,%1,%2,%3}, {%4,%5}, {%6}, {%0,%1,%2,%3};"
        : "+f"(d[0]), "+f"(d[1]), "+f"(d[2]), "+f"(d[3]) : "r"(a0), "r"(a1), "r"(b0));
}
__device__ __forceinline__ void ldsm4(uint32_t a, uint32_t* r) {
    asm volatile("ldmatrix.sync.aligned.m8n8.x4.shared.b16 {%0,%1,%2,%3}, [%4];" : "=r"(r[0]), "=r"(r[1]), "=r"(r[2]), "=r"(r[3]) : "r"(a));
}
__device__ __forceinline__ void ldsm4t(uint32_t a, uint32_t* r) {
    asm volatile("ldmatrix.sync.aligned.m8n8.x4.trans.shared.b16 {%0,%1,%2,%3}, [%4];" : "=r"(r[0]), "=r"(r[1]), "=r"(r[2]), "=r"(r[3]) : "r"(a));
}
__device__ __forceinline__ uint32_t nz(uint32_t v) { uint32_t r; asm("max.u32 %0, %1, 1;" : "=r"(r) : "r"(v)); return r; }
__device__ __forceinline__ float rcp(float x) { float r; asm("rcp.approx.ftz.f32 %0, %1;" : "=f"(r) : "f"(x)); return r; }
__device__ __forceinline__ uint2 ld_relaxed2(const void* p) { uint2 v; asm volatile("ld.relaxed.gpu.global.v2.u32 {%0,%1}, [%2];" : "=r"(v.x), "=r"(v.y) : "l"(p) : "memory"); return v; }
__device__ __forceinline__ void st_relaxed2(void* p, uint32_t x, uint32_t y) { asm volatile("st.relaxed.gpu.global.v2.u32 [%0], {%1,%2};" ::"l"(p), "r"(max(x, 1u)), "r"(max(y, 1u)) : "memory"); }
__host__ __device__ constexpr uint64_t dconst(uint32_t lbo, uint32_t sbo, uint32_t swz) {
    return ((uint64_t)(lbo >> 4) << 16) | ((uint64_t)(sbo >> 4) << 32) | ((uint64_t)swz << 62);
}
__device__ __forceinline__ uint32_t mkdesc(uint32_t addr, uint64_t c) { return (uint32_t)c | ((addr & 0x3FFFF) >> 4); }
#define WG_FENCE() asm volatile("wgmma.fence.sync.aligned;" ::: "memory")
#define WG_COMMIT() asm volatile("wgmma.commit_group.sync.aligned;" ::: "memory")
#define WG_WAIT(n) asm volatile("wgmma.wait_group.sync.aligned %0;" ::"n"(n) : "memory")
template <int N> __device__ __forceinline__ void reg_fence(float* d) {
#pragma unroll
    for (int i = 0; i < N; i++) asm volatile("" : "+f"(d[i])::"memory");
}
template <int N> __device__ __forceinline__ void reg_def(float* d) {
#pragma unroll
    for (int i = 0; i < N; i++) asm volatile("" : "=f"(d[i]));
}
template <int N> __device__ __forceinline__ void reg_def(uint32_t* d) {
#pragma unroll
    for (int i = 0; i < N; i++) asm volatile("" : "=r"(d[i]));
}
__device__ __forceinline__ bool is_unset(uint4 v) { return min(min(v.x, v.y), min(v.z, v.w)) == 0u; }
__device__ __forceinline__ uint4 nz4(uint32_t a, uint32_t b, uint32_t c, uint32_t d) { return make_uint4(max(a, 1u), max(b, 1u), max(c, 1u), max(d, 1u)); }
__device__ __forceinline__ void wait_flags(const uint32_t* p, uint32_t target, uint32_t mask) {
    int n = 0;
    while (~__ballot_sync(~0u, (int)(ld_relaxed(p) - target) >= 0) & mask) { if (++n > SPIN_LIMIT) __trap(); }
    asm volatile("fence.acquire.gpu;" ::: "memory");
}
__device__ __forceinline__ float silu_bf(uint32_t cbits) {
    const float c = __uint_as_float(cbits << 16);
    return bf_round(__fdividef(c, 1.f + fminf(ex2(-1.4426950408889634f * c), 1e30f)));
}
__device__ __forceinline__ void gemv_part(uint32_t wmbuf, int wp, int lane) {
    const uint32_t wa = wmbuf + wp * 512 + (8 * (lane >> 4) + (lane & 7)) * 32 + ((lane >> 3) & 1) * 16;
    float d[4] = {};
#pragma unroll
    for (int i = 0; i < 4; i++) {
        uint32_t A[4];
        const float2 v = lds2f(wmbuf + 28672 + (wp + 8 * i) * 32 + (lane & 3) * 8);
        ldsm4t(wa + (i < 3 || wp < 4 ? i : 0) * 4096, A);
        mma16816(d, A[0], A[1], A[2], A[3], __float_as_uint(v.x), __float_as_uint(v.y));
    }
    if ((lane & 3) == 0) {
        sts1(wmbuf + 29696 + (wp * 16 + (lane >> 2)) * 4, __float_as_uint(d[0]));
        sts1(wmbuf + 29696 + (wp * 16 + 8 + (lane >> 2)) * 4, __float_as_uint(d[2]));
    }
}
__device__ __forceinline__ uint32_t mod_word(float v, int col, uint32_t target) {
    v = bf_round(v);
    if ((col >= DM && col < 2 * DM) || (col >= 4 * DM && col < 5 * DM)) v += 1.f;
    return (pack2(v, 0.f) << 16) | (target & 0xFFFFu);
}
__device__ __forceinline__ const uint4* mod_src(int i, int r, int j, bool p2) {
    i = min(i, p2 ? 251 : 223);
    return (const uint4*)g_mod + (r & 7) * (6 * DM / 4) + (i < 224 ? (p2 ? 336 : 0) + i : (i < 238 ? 14 * j + i : 14 * j + i + 322));
}
__device__ __forceinline__ void mod_store(uint32_t sb, uint4 v, const uint4* src, int i) {
    const uint32_t tag = lds1(sb + M_EPOCH) + 1;
    while (__any_sync(~0u, (((v.x ^ tag) | (v.y ^ tag) | (v.z ^ tag) | (v.w ^ tag)) & 0xFFFFu) != 0u)) v = ld_relaxed4(src);
    if (i < 224) {
        const int isc = i >= 112, c4 = i - 112 * isc;
        const uint32_t a = sb + M_ST + (c4 >> 2) * 64 + (c4 & 1) * 32 + (c4 & 2) * 4 + (isc ? 0 : 4);
        sts1(a, __byte_perm(v.x, v.y, 0x7632));
        sts1(a + 16, __byte_perm(v.z, v.w, 0x7632));
    } else if (i < 252) {
        sts4(sb + M_G + (i - 224) * 16, make_uint4(v.x & 0xFFFF0000u, v.y & 0xFFFF0000u, v.z & 0xFFFF0000u, v.w & 0xFFFF0000u));
    }
}
__device__ __forceinline__ int pass_f(int fs, int ps) { return 224 * fs + ((fs & 1) ? (ps == 0 ? 96 : ps == 1 ? 32 : 0) : (ps == 0 ? 0 : ps == 1 ? 128 : 192)); }
__device__ __forceinline__ constexpr uint32_t slot_off(int l) { return l * 16384; }
__device__ __forceinline__ constexpr int g1_slot(int s) { return s % 7; }
__device__ __noinline__ void x1_fix(const uint32_t* g, uint32_t sa, int s) {
#pragma unroll 1
    for (int k = 4 * s; k < 4 * s + 4;) {
        const uint4 v = ld_relaxed4((const uint4*)(g + k * 256));
        sts4(sa + k * 1024, v);
        k += 2 * __all_sync(~0u, min(min(v.x, v.y), min(v.z, v.w)) != 0u);
    }
    __syncwarp();
}
__device__ __forceinline__ void ln_coeffs(float mean, float msq, uint32_t& r2, uint32_t& n2) {
    const float rs = bf_round(rsqrtf(fmaxf(msq - mean * mean, 0.f) + 1e-5f));
    r2 = pack2(rs, rs);
    n2 = pack2(-mean * rs, -mean * rs);
}

#define LOADW bulk_e(dst, g_wd + (size_t)((f >> 5) * 4 + nq) * 1792, 7168, bar);
template <int sec> __device__ __forceinline__ void ring_loader(const Params& p, uint32_t sb_, int r_, int j_, int lane) {
    const uint32_t sb = opaque(sb_);
    const int r = opaque(r_), j = opaque(j_), nq = j >> 1, fs = 4 * (j & 1) + nq;
    const int fa = pass_f(fs, 0), fb = pass_f(fs, 1), fc = pass_f(fs, 2);
    const uint32_t* h2src = (const uint32_t*)__shfl_sync(~0u, (unsigned long long)(p.actb + (size_t)r * RB_WORDS + RB_H2), 0);
    const CUtensorMap* gmap = (const CUtensorMap*)__shfl_sync(~0u, (unsigned long long)(&p.ga + sec), 0);
#define BAR(i) (sb + M_BAR + 8 * (i))
#define kh (j & 1)
            int sl = 0;
#pragma unroll 1
            for (int s = 0; s < 28; s++) {
                if (s == 7) { wait_flags(g_flag + (8 * r + j) * 128 + 96 + lane, lds1(sb + M_EPOCH) + 1, 0xFFFFu); fence_async_global(); }
                const int ps = s < 14 ? 0 : s < 21 ? 1 : 2;
                const uint32_t half = ps < 2 ? 8192 : 4096;
                const int sp = sl;
                if (s >= PACE && s < PACE_END) mbar_wait(BAR(B_FULL + s - PACE), 0);
                mbar_wait(BAR(B_EMPTY + sp), (s >= 7 && s < 14) || s >= 21);
                expect_e(BAR(B_FULL + sp), half);
                tma3_e(sb + slot_off(sp) + sec * half, gmap + 2 * ps, 0, ps ? 64 * sl : 32 * s, ps == 0 ? fa >> 6 : ps == 1 ? fb >> 6 : fc >> 5, BAR(B_FULL + sp));
                sl = sl == 6 ? 0 : sl + 1;
            }
            if (!sec) PROFH(3);
#pragma unroll 1
            for (int e = 0; e < 4; e++) {
                const uint32_t dst = sb + slot_off(e) + sec * 8192, bar = BAR(B_FULL + e);
                const int f = (e < 2 ? fa + 64 * e : e == 2 ? fb : fc) + 32 * sec;
                mbar_wait(BAR(B_EMPTY + e), 0);
                expect_e(bar, e == 3 && sec ? 0 : 7168);
                if (!(e == 3 && sec)) { LOADW }
            }
            sl = 4;
            int e = 4;
#pragma unroll 1
            for (int grp = 0; grp < 9; grp++) {
                const int ps = grp >= 6 ? 2 : grp >= 3 ? 1 : 0;
                int sidx = grp - 3 * ps;
                if (sec && sidx == 0) { mbar_wait(BAR(B_HRDY + ps), 0); fence_async_global(); }
                sidx += sidx >= nq;
                int f = pass_f(4 * kh + sidx, ps);
#pragma unroll 1
                for (int k = 4 >> ps; k > 0; k--, e++, f += 32) {
                    const uint32_t dst = sb + slot_off(sl), bar = BAR(B_FULL + sl);
                    mbar_wait(BAR(B_EMPTY + sl), e >= 12 && e < 24);
                    if (e < WIN_END && e >= WIN) mbar_wait(BAR(B_FULL + (sl >= WIN ? sl - WIN : sl + 12 - WIN)), e - WIN >= 12);
                    expect_e(bar, sec ? 8192 : 7168);
                    if (!sec) { LOADW }
                    else bulk_e(dst + 8192, h2src + f * 64, 8192, bar);
                    sl = sl == 11 ? 0 : sl + 1;
                }
            }
            if (!sec) PROFH(4);
}

#define PROF_PARAMS
#define PROF_ARGS
__device__ __noinline__ void helper_late(const Params& p, int r_, int j_, int warp_ PROF_PARAMS) {
    extern __shared__ __align__(1024) unsigned char smem[];
    const uint32_t sb = (uint32_t)__cvta_generic_to_shared(smem);
    const int r = opaque(r_), j = opaque(j_), warp = opaque(warp_), nq = j >> 1, b = 8 * r + j;
    uint32_t* const act = (uint32_t*)__shfl_sync(~0u, (unsigned long long)(p.actb + (size_t)r * RB_WORDS), 0);
    {
        const int lane = fresh_tid() & 31;
        const uint32_t target = lds1(sb + M_EPOCH) + 1;
        if (warp == 8) { expect_e(BAR(B_XCH), 14336); expect_e(BAR(B_XCH + 1), 14336); }
            if (warp == 9) {
#pragma unroll 1
                for (int kv = 0; kv < 2; kv++) {
                    mbar_wait(BAR(B_PUB + kv), 0);
                    wait_flags(g_flag + b * 128 + lane, target, (r >= 2 ? 6u : r == 1 ? 2u : 0u) << (8 * kv));
                    fence_async_global();
                    const uint32_t dst = sb + OFF_Y + (kv ? Y_VR : Y_K);
                    expect_e(BAR(B_KRFULL + kv), r >= 2 ? 28672 : r == 1 ? 14336 : 0);
                    if (r >= 2) bulk_e(dst, act - 2 * RB_WORDS + RB_KV + j * 7168 + kv * 3584, 14336, BAR(B_KRFULL + kv));
                    if (r >= 1) bulk_e(dst + 14336, act - RB_WORDS + RB_KV + j * 7168 + kv * 3584, 14336, BAR(B_KRFULL + kv));
                }
            } else if (warp == 8) {
                uint4 v[8];
                mbar_wait(BAR(B_WOFULL), 0);
#pragma unroll
                for (int k = 0; k < 8; k++) v[k] = ld_relaxed4(mod_src(lane + 32 * k, r, j, true));
#pragma unroll
                for (int k = 0; k < 8; k++) mod_store(sb, v[k], mod_src(lane + 32 * k, r, j, true), lane + 32 * k);
                warp_arrive(BAR(B_MOD1));
            } else if (warp == 11) {
                if (kh == 1 && r < 14) {
                    const uint32_t wmbuf = sb + OFF_X + HALF;
                    const int mcol = 2 * DM + 32 * (4 * r + nq);
                    mbar_wait(BAR(B_XFREE), 0);
#pragma unroll 1
                    for (int wd = lane; wd < 224; wd += 32) {
                        const uint32_t cb = __ldg((const uint32_t*)p.c + wd);
                        sts1(wmbuf + 28672 + (wd >> 3) * 32 + (wd & 3) * 8 + (wd & 4), pack2(silu_bf(cb & 0xFFFFu), silu_bf(cb >> 16)));
                    }
                    __syncwarp();
                    mbar_wait(BAR(B_WMFULL), 0);
                    const uint32_t wa = wmbuf + (8 * (lane >> 4) + (lane & 7)) * 32 + ((lane >> 3) & 1) * 16;
                    float d[2][4] = {};
#pragma unroll 4
                    for (int ks = 0; ks < 28; ks++) {
                        uint32_t A[8];
                        ldsm4t(wa + ks * 512, A); ldsm4t(wa + 14336 + ks * 512, A + 4);
                        const float2 v = lds2f(wmbuf + 28672 + ks * 32 + (lane & 3) * 8);
                        mma16816(d[0], A[0], A[1], A[2], A[3], __float_as_uint(v.x), __float_as_uint(v.y));
                        mma16816(d[1], A[4], A[5], A[6], A[7], __float_as_uint(v.x), __float_as_uint(v.y));
                    }
                    const int q = lane & 3, col = mcol + 8 * q + (lane >> 2);
                    const uint32_t word = mod_word(q == 0 ? d[0][0] : q == 1 ? d[0][2] : q == 2 ? d[1][0] : d[1][2], col, target);
#pragma unroll
                    for (int i = 0; i < 8; i++) st_relaxed(g_mod + i * 6 * DM + col, word);
                }
                warp_arrive(BAR(B_WMFREE));
                mbar_wait(BAR(B_VRFULL), 0);
                l2_prefetch_e((const char*)p.wg + (size_t)b * 12544, 12544);
                l2_prefetch_e((const char*)p.wu + (size_t)b * 12544, 12544);
#pragma unroll 1
                for (int k = 0; k < (r < 12 ? 2 : 1); k++) {
                    const int u = 28 * kh + r + 16 * k;
                    expect_e(BAR(B_XFULL + k), 7168);
                    tma3_e(sb + OFF_Y + 102400, &p.dn, 0, 32 * u, 7 * j, BAR(B_XFULL + k));
                    tma3_e(sb + OFF_Y + 102400 + 3584, &p.dn, 0, 32 * u, 7 * (j ^ 1), BAR(B_XFULL + k));
                    mbar_wait(BAR(B_XFULL + k), 1);
                    asm volatile("{\n.reg .pred p;\nelect.sync _|p, 0xffffffff;\n@p cp.async.bulk.global.shared::cta.bulk_group [%0], [%1], 7168;\n"
                                 "cp.async.bulk.commit_group;\ncp.async.bulk.wait_group 0;\n}" ::"l"(g_wd + (size_t)(u * 4 + nq) * 1792), "r"(sb + OFF_Y + 102400) : "memory");
                    __syncwarp();
                }
                warp_arrive(BAR(B_WMFREE));
                fence_gpu();
                if (lane < 16) st_relaxed(g_flag + (8 * lane + j) * 128 + 96 + r, target);
            }
        if (warp == 8 || warp == 11) {
            const int sec = warp == 11;
            if (sec) ring_loader<1>(p, sb, r, j, lane); else ring_loader<0>(p, sb, r, j, lane);
            mbar_wait(BAR(B_DONE), 0);
        } else if (warp == 9) {
#pragma unroll
            for (int ev = 0; ev < 4; ev++) { expect_e(BAR(B_GFULL + ev), ev < 2 ? HALF / 2 : 16384 + 4096); expect_e(BAR(B_XFULL + 2 + ev), ev < 2 ? HALF / 2 : HALF - 16384); }
            mbar_wait(BAR(B_PUB + 2), 0);
            const uint32_t* fp = g_flag + b * 128 + 32 + lane;
            const int par = (target - 1) & 1;
#pragma unroll 1
            for (int n = 0, ev = 0; ev < 4; n++) {
                if (ev == 1) { mbar_wait(BAR(B_WMFREE), 1); mbar_wait(BAR(B_PUB + 3), 0); }
                uint32_t ok = __ballot_sync(~0u, (int)(ld_relaxed(fp) - target) >= 0) >> (8 * ev);
                while ((ok & 0xFFu) == 0xFFu) {
                    asm volatile("fence.acquire.gpu;" ::: "memory");
                    fence_async_global();
                    const int tile = (ev & 1) + (ev >> 1) * par * 2;
                    const uint32_t dst = sb + (ev == 0 ? OFF_X : OFF_Y + (ev & 1) * HALF), first = ev < 2 ? HALF / 2 : 16384;
                    const char* src = (const char*)(act + RB_O + ((ev >> 1) * 2 + tile) * 14336);
                    if (ev >= 2) bulk_e(sb + OFF_X + X_STAT + (ev & 1) * 49152, act + RB_ST + tile * 1024, 4096, BAR(B_GFULL + ev));
                    bulk_e(dst, src, first, BAR(B_GFULL + ev));
                    bulk_e(dst + first, src + first, HALF - first, BAR(B_XFULL + 2 + ev));
                    if (ev) PROFH(4 + ev);
                    ev++; ok >>= 8;
                }
                if (n > SPIN_LIMIT) __trap();
            }
            mbar_wait(BAR(B_XFULL + 5), 1);
#pragma unroll 1
            for (int hf = 0; hf < 2; hf++) {
                const int tile = (par ^ 1) * 2 + hf;
                uint4* xz = (uint4*)(act + RB_X1 + tile * 14336 + j * 1792) + lane;
#pragma unroll
                for (int i = 0; i < 14; i++) xz[i * 32] = make_uint4(0, 0, 0, 0);
                ((uint4*)(act + RB_ST + (tile * 8 + j) * 128))[lane] = make_uint4(0, 0, 0, 0);
            }
#pragma unroll 1
            for (int ps = 0; ps < 3; ps++) {
                mbar_wait(BAR(B_PUB + 6 + ps), 0);
                wait_flags(g_flag + b * 128 + 64 + lane, target, (0x55u << kh) << (8 * ps));
                warp_arrive(BAR(B_HRDY + ps));
                PROFH(9 + ps);
            }
        } else {
#pragma unroll 1
            for (int k = 0; k < 9; k++) {
                uint32_t* fp = k < 2 ? g_flag + (b + 8 * lane) * 128 + k * 8 + lane : g_flag + (8 * r + lane) * 128 + 16 + k * 8 + j;
                mbar_wait(BAR(B_PUB + k), 0);
                if (k != 4 && k != 5) fence_gpu();
                if (k < 2 ? (lane == 1 || lane == 2) : lane < 8) st_relaxed(fp, target);
                if (k >= 3 && k <= 5) PROFH(k - 3);
            }
        }
    }
}

__global__ void __cluster_dims__(2, 1, 1) __launch_bounds__(384, 1) fused_block_kernel(const __grid_constant__ Params p) {
    extern __shared__ __align__(1024) unsigned char smem[];
    const uint32_t sb = (uint32_t)__cvta_generic_to_shared(smem);
    const int tid = threadIdx.x, lane = tid & 31, warp = __shfl_sync(~0u, tid >> 5, 0);
    const int m = blockIdx.x >> 1;
    int r, nq;
    if (m < 4) { r = 15; nq = m; }
    else if (m < 36) { r = (m - 4) & 7; nq = (m - 4) >> 3; }
    else { nq = (m - 36) / 7; r = m - 28 - 7 * nq; }
    const int j = opaque(2 * nq + (blockIdx.x & 1)), b = 8 * r + j, fs = 4 * kh + nq;
#define act (p.actb + (size_t)r * RB_WORDS)
    constexpr uint32_t sc = 0;
    if (lane == 0 && warp < 9 && warp != 6 && warp != 7) {
        const int i0 = warp == 8 ? 0 : 8 + 8 * warp, cnt = warp == 0 || warp == 8 ? 1 : warp < 3 ? 2 : 8;
#pragma unroll
        for (int k = 0; k < 8; k++) if (i0 + k != B_WMFULL) mbar_init(BAR(i0 + k), cnt);
        asm volatile("fence.mbarrier_init.release.cluster;" ::: "memory");
        fence_async_smem();
    }

    if (warp >= 8) {
        const int lane = fresh_tid() & 31;
        const bool early = kh == 0, gemv = r < 14;
        const int mcol = early ? 16 * (4 * r + nq) : 2 * DM + 32 * (4 * r + nq);
        const uint32_t wmbuf = sb + OFF_Y + HALF;
        asm volatile("setmaxnreg.dec.sync.aligned.u32 56;");
        if (warp == 9) {
#pragma unroll
            for (int i = 56; i < 64; i++) init_e(BAR(i), 1);
            fence_async_smem();
        }
        if (warp == 8) { init_e(BAR(B_WMFULL), 1); fence_async_smem(); }
        bar_arrive(0, 384);
        asm volatile("barrier.cluster.arrive.relaxed.aligned;" ::: "memory");
        if (warp == 8) {
            if (!sc) {
                expect_e(BAR(B_WMFULL), gemv ? 28672 >> early : 0);
                if (early && gemv) { tma3_e(wmbuf, &p.wm, mcol, 0, 0, BAR(B_WMFULL)); tma3_e(wmbuf + 7168, &p.wm, mcol, 224, 0, BAR(B_WMFULL)); }
#pragma unroll 1
                for (int kb = 0; kb < 7; kb++) {
                    expect_e(BAR(B_XFULL + kb), 16384);
                    tma3_e(sb + OFF_X + kb * 16384, &p.xm, 64 * kb, 128 * r, 0, BAR(B_XFULL + kb));
                }
            }
#pragma unroll 1
            for (int mt = 0; mt < 4; mt++) {
                if (mt == 1) bar_sync(9, 384);
                if (mt == 3) {
                    if (!early && gemv) {
#pragma unroll 1
                        for (int k = 0; k < 4; k++) tma3_e(sb + OFF_X + HALF + k * 7168, &p.wm, mcol + (k >> 1) * 16, (k & 1) * 224, 0, BAR(B_WMFULL));
                    }
                    mbar_wait(BAR(B_WMFREE), 0);
                }
                if (mt) mbar_wait(BAR(mt == 1 ? B_MOD1 : mt == 2 ? B_XFREE : B_VRFULL), 0);
                const uint32_t bar = BAR(mt == 3 ? B_WOFULL : B_FULLK + mt), dst = sb + (mt < 2 ? OFF_Y : OFF_X) + (mt & 1) * HALF;
                const int c0 = (mt < 2 ? DM + DM * mt : 0) + 56 * j - 8 * kh;
                if (!sc) {
                    expect_e(bar, HALF);
                    tma3_e(dst, mt == 3 ? &p.wo : &p.qkv, c0, 0, 0, bar);
                    tma3_e(dst + HALF / 2, mt == 3 ? &p.wo : &p.qkv, c0, 224, 0, bar);
                }
            }
        } else {
            if (warp == 10 && !sc) l2_prefetch_e((const char*)p.wqkv + (size_t)b * 9408, 9408);
            bar_sync(9, 384);
            if (sc) return;
            if (warp == 11 && early) {
                const uint32_t target = lds1(sb + M_EPOCH) + 1;
                mbar_wait(BAR(B_GEMV), 0);
                float sum = 0.f;
#pragma unroll
                for (int i = 0; i < 8; i++) sum += *(const float*)(smem + OFF_Y + HALF + 29696 + (i * 16 + (lane & 15)) * 4);
                uint32_t* mg = g_mod + mcol + (lane & 15) + (lane >> 4) * 4 * 6 * DM;
                const uint32_t word = mod_word(sum, mcol, target);
                if (gemv) { st_relaxed(mg, word); st_relaxed(mg + 6 * DM, word); st_relaxed(mg + 12 * DM, word); st_relaxed(mg + 18 * DM, word); }
            }
        }
    }
    if (LIKELY(warp < 8)) {
        const int w = warp >> 2, wi = warp & 3;
#define COORDS const int t = fresh_tid() & 127, lane = t & 31, q = lane & 3, lr = lane >> 2, ra = 64 * w + 16 * wi + lr; \
        const uint32_t lx = (lane >> 4) ^ (lane & 7), mrow = (64 * w + 16 * wi + ((lane >> 3) & 1) * 8 + (lane & 7)) * 128; \
        (void)q; (void)lr; (void)ra; (void)lx; (void)mrow;
        const int sid = 2 * (j & 3) + w;
#define RUN(k) (!sc || sid == (k))
#define WAIT(i, par) mbar_wait_c(BAR(i), (par) | sc)
        constexpr uint64_t DB128 = dconst(4096, 1024, 1);
        {
            const int wd = fresh_tid();
            const uint32_t cb = wd < 224 ? __ldg((const uint32_t*)p.c + wd) : 0u;
            if (wd == 255 && !sc) sts1(sb + M_EPOCH, atomicAdd(&g_ticket, 1u) / NCTA);
            sts1(sb + OFF_Y + HALF + 28672 + (wd >> 3) * 32 + (wd & 3) * 8 + (wd & 4), pack2(silu_bf(cb & 0xFFFFu), silu_bf(cb >> 16)));
        }
        bar_arrive(9, 384);
        bar_sync(0, 384);
        asm volatile("barrier.cluster.arrive.relaxed.aligned;" ::: "memory");
        asm volatile("setmaxnreg.inc.sync.aligned.u32 224;");
        PROFC(0);
        uint32_t xr[16];
        {
            COORDS
            uint32_t h[112];
            uint32_t ra2, na2, rb2, nb2;
            const int mi = min(128 * w + t, 223);
            const uint4* msrc = mod_src(mi, r, j, false);
            uint4 mv;
            {
                float ds[4] = {}, da[2][4] = {}, db[2][4] = {};
                const uint32_t ONE2 = 0x3F803F80u;
#pragma unroll
                for (int kb = 0; kb < 7; kb++) {
                    if (kb == GEMV_AT && kh == 0) { WAIT(B_WMFULL, 0); gemv_part(sb + OFF_Y + HALF, warp, lane); warp_arrive(BAR(B_GEMV)); }
                    WAIT(B_XFULL + kb, 0);
#pragma unroll
                    for (int k4 = 0; k4 < 4; k4++) ldsm4(sb + OFF_X + mrow + kb * 16384 + (((2 * k4) ^ lx) << 4), h + 16 * kb + 4 * k4);
#pragma unroll
                    for (int k4 = 0; k4 < 4; k4++) {
                        const uint32_t* f = h + 16 * kb + 4 * k4;
                        mma16816(ds, f[0], f[1], f[2], f[3], ONE2, ONE2);
                        mma1688(da[0], f[0], f[1], f[0]); mma1688(db[0], f[0], f[1], f[1]);
                        mma1688(da[1], f[2], f[3], f[2]); mma1688(db[1], f[2], f[3], f[3]);
                    }
                }
#pragma unroll
                for (int i = 0; i < 4; i++) {
                    const int ch = 7 * j + 2 * i + (lane >> 4);
                    ldsm4(sb + OFF_X + mrow + (ch >> 3) * 16384 + (((ch ^ lane) & 7) << 4), xr + 4 * i);
                }
                mv = ld_relaxed4(msrc);
                warp_arrive(BAR(B_XFREE));
                float qa = (lr & 1) ? da[0][1] + da[1][1] : da[0][0] + da[1][0];
                float qb = (lr & 1) ? db[0][3] + db[1][3] : db[0][2] + db[1][2];
                const int src = (lane & ~3) | (lr >> 1);
                qa = __shfl_sync(~0u, qa, src);
                qb = __shfl_sync(~0u, qb, src);
                ln_coeffs(ds[0] * (1.f / DM), qa * (1.f / DM), ra2, na2);
                ln_coeffs(ds[2] * (1.f / DM), qb * (1.f / DM), rb2, nb2);
#pragma unroll
                for (int i = 0; i < 4 * NPRE; i += 2) { h[i] = hfma2(h[i], ra2, na2); h[i + 1] = hfma2(h[i + 1], rb2, nb2); }
            }
            PROFC(1);
            {
                float ak[28], av[28], aq[28];
                uint32_t kp[14], vp[14];
                const uint64_t bq0 = (DB128 & ~0xFFFFFFFFull) | (mkdesc(sb + OFF_X, DB128) + kh), bk0 = bq0 + (OFF_Y >> 4), bv0 = bk0 + (HALF >> 4);
                uint32_t* kvg = act + RB_KV + j * 7168 + (8 * w + 2 * wi) * 224 + lane;
                mod_store(sb, mv, msrc, mi);
                bar_sync(3, 256);
                if (warp == 0) warp_arrive(BAR(B_MOD1));
                WAIT(B_FULLK, 0);
                PROFC(2);
                reg_def<28>(ak);
#pragma unroll
                for (int g4 = 0; g4 < 4; g4++) {
#pragma unroll
                    for (int ks = 7 * g4; ks < 7 * g4 + 7; ks++) {
                        const uint4 st = *(const uint4*)(smem + M_ST + ks * 64 + q * 16);
                        if (ks >= NPRE) {
                            h[4 * ks] = hfma2(h[4 * ks], ra2, na2); h[4 * ks + 1] = hfma2(h[4 * ks + 1], rb2, nb2);
                            h[4 * ks + 2] = hfma2(h[4 * ks + 2], ra2, na2); h[4 * ks + 3] = hfma2(h[4 * ks + 3], rb2, nb2);
                        }
                        h[4 * ks] = hfma2(h[4 * ks], st.x, st.y); h[4 * ks + 1] = hfma2(h[4 * ks + 1], st.x, st.y);
                        h[4 * ks + 2] = hfma2(h[4 * ks + 2], st.z, st.w); h[4 * ks + 3] = hfma2(h[4 * ks + 3], st.z, st.w);
                    }
                    WG_FENCE();
#pragma unroll
                    for (int ks = 7 * g4; ks < 7 * g4 + 7; ks++) wgmma_rl_56(ak, h[4 * ks], h[4 * ks + 1], h[4 * ks + 2], h[4 * ks + 3], bk0 + ks * 128, ks != 0);
                }
                WG_COMMIT();
                PROFC(3);
                WAIT(B_FULLV, 0);
                reg_def<28>(av);
                WG_FENCE();
#pragma unroll
                for (int ks = 0; ks < 8; ks++) wgmma_rl_56(av, h[4 * ks], h[4 * ks + 1], h[4 * ks + 2], h[4 * ks + 3], bv0 + ks * 128, ks != 0);
                WG_COMMIT();
                WG_WAIT(1);
                reg_fence<28>(ak);
#pragma unroll
                for (int g = 0; g < 7; g++) {
                    kp[2 * g] = pack2(ak[4 * g], ak[4 * g + 1]); kp[2 * g + 1] = pack2(ak[4 * g + 2], ak[4 * g + 3]);
                    kvg[g * 32] = kp[2 * g]; kvg[224 + g * 32] = kp[2 * g + 1];
                }
                warp_arrive(BAR(B_PUB));
                PROFC(4);
                WG_FENCE();
#pragma unroll
                for (int ks = 8; ks < 28; ks++) wgmma_rl_56(av, h[4 * ks], h[4 * ks + 1], h[4 * ks + 2], h[4 * ks + 3], bv0 + ks * 128, 1);
                WG_COMMIT();
                WAIT(B_FULLQ, 0);
                reg_def<28>(aq);
                WG_FENCE();
#pragma unroll
                for (int ks = 0; ks < 8; ks++) wgmma_rl_56(aq, h[4 * ks], h[4 * ks + 1], h[4 * ks + 2], h[4 * ks + 3], bq0 + ks * 128, ks != 0);
                WG_COMMIT();
                WG_WAIT(1);
                reg_fence<28>(av);
#pragma unroll
                for (int g = 0; g < 7; g++) {
                    vp[2 * g] = pack2(av[4 * g], av[4 * g + 1]); vp[2 * g + 1] = pack2(av[4 * g + 2], av[4 * g + 3]);
                    kvg[3584 + g * 32] = vp[2 * g]; kvg[3584 + 224 + g * 32] = vp[2 * g + 1];
                }
                warp_arrive(BAR(B_PUB + 1));
                PROFC(5);
                WG_FENCE();
#pragma unroll
                for (int ks = 8; ks < 28; ks++) wgmma_rl_56(aq, h[4 * ks], h[4 * ks + 1], h[4 * ks + 2], h[4 * ks + 3], bq0 + ks * 128, 1);
                WG_COMMIT();
                WAIT(B_PUB + 1, 0);
                const uint32_t rg = 8 * w + 2 * wi + ((lane >> 3) & 1);
                const uint32_t ko = sb + OFF_Y + Y_KOWN + rg * 896 + (lane & 7) * 16, qo = sb + OFF_Y + Y_Q + rg * 1024 + (lane >> 4) * 128 + (lane & 7) * 16;
#pragma unroll
                for (int g = 0; g < 6; g += 2) {
                    stsm4(ko + (g + (lane >> 4)) * 128, kp[2 * g], kp[2 * g + 1], kp[2 * g + 2], kp[2 * g + 3]);
                    stsm4(ko + (Y_VOWN - Y_KOWN) + (g + (lane >> 4)) * 128, vp[2 * g], vp[2 * g + 1], vp[2 * g + 2], vp[2 * g + 3]);
                }
                stsm4(ko + (lane >> 4) * (Y_VOWN - Y_KOWN) + 6 * 128, kp[12], kp[13], vp[12], vp[13]);
                WG_WAIT(0);
                reg_fence<28>(aq);
                __syncwarp();
                if (lane < 3 && w == 1) mbar_arrive(BAR(B_EMPTY + lane));
                uint32_t qp[14];
#pragma unroll
                for (int i = 0; i < 14; i++) qp[i] = pack2(aq[2 * i], aq[2 * i + 1]);
                stsm4(qo, qp[0], qp[1], qp[2], qp[3]);
                stsm4(qo + 256, qp[4], qp[5], q < 2 ? qp[6] : 0u, q < 2 ? qp[7] : 0u);
                stsm4(qo + 512, q < 2 ? 0u : qp[6], q < 2 ? 0u : qp[7], qp[8], qp[9]);
                stsm4(qo + 768, qp[10], qp[11], qp[12], qp[13]);
                if (!sc) bar_sync(3, 256);
            }
        }
        PROFC(6);
        WAIT(B_KRFULL, 0);
        PROFC(7);
        if (RUN(2)) {
#pragma unroll 1
            for (int hf = sc; hf < 2; hf++) {
                COORDS
                float s[136];
                float na = 0.f, nb = 0.f;
                const float CS = 0.18898223650461361f * 1.4426950408889634f;
                const int kg0 = 8 * hf + 2 * wi;
                const int pmin = 16 - 8 * r - 4 * hf - wi;
                const float NEG = __int_as_float(0xFF800000);
                {
                    uint32_t F[8];
                    const uint32_t qa = sb + OFF_Y + Y_Q + (kg0 + ((lane >> 3) & 1)) * 1024 + (4 * w + (lane >> 4)) * 128 + (lane & 7) * 16;
                    ldsm4(qa, F); ldsm4(qa + 256, F + 4);
                    uint32_t ka = sb + OFF_Y + Y_K + kg0 * 896 + (3 * w + (lane >> 3)) * 128 + (lane & 7) * 16;
#pragma unroll
                    for (int g = 0; g < 34; g++) {
                        uint32_t B[4];
                        if (g >= 12 && g % 4 == 0) ka += __float_as_uint(s[4 * (g - 12)]) & p.zero;
                        ldsm4(ka + g * 896, B);
                        mma16816_first(s + 4 * g, F[0], F[1], F[2], F[3], B[0], B[1]);
                        mma16816_v(s + 4 * g, F[4], F[5], F[6], F[7], B[2], B[3]);
                    }
                    const bool c0 = 2 * q > lr, c1 = 2 * q + 1 > lr;
                    if (!c0) { s[0] = NEG; s[6] = NEG; }
                    if (!c1) { s[1] = NEG; s[7] = NEG; }
                    s[2] = NEG; s[3] = NEG;
                    if (c0) { s[128] = NEG; s[134] = NEG; }
                    if (c1) { s[129] = NEG; s[135] = NEG; }
                    s[132] = NEG; s[133] = NEG;
                    float ma = NEG, mb = NEG;
#pragma unroll
                    for (int pp = 0; pp < 17; pp++) {
                        const float* e = s + 8 * pp;
                        const float bias = pp < pmin ? NEG : 0.f;
                        ma = fmaxf(ma, fmaxf(fmaxf(e[0], e[1]), fmaxf(e[4], e[5])) + bias);
                        mb = fmaxf(mb, fmaxf(fmaxf(e[2], e[3]), fmaxf(e[6], e[7])) + bias);
                    }
                    ma = fmaxf(ma, __shfl_xor_sync(~0u, ma, 1)); mb = fmaxf(mb, __shfl_xor_sync(~0u, mb, 1));
                    ma = fmaxf(ma, __shfl_xor_sync(~0u, ma, 2)); mb = fmaxf(mb, __shfl_xor_sync(~0u, mb, 2));
                    na = -ma * CS; nb = -mb * CS;
                }
                PROFC(8 + 3 * hf);
                {
                    WAIT(B_VRFULL, 0);
                    float o[16] = {}, rs[4] = {};
                    uint32_t pk[2];
                    const uint32_t va = sb + OFF_Y + Y_VR + (kg0 + ((lane >> 3) & 1)) * 896 + (3 * w + (lane >> 4)) * 128 + (lane & 7) * 16;
#pragma unroll
                    for (int pp = 0; pp < 17; pp++) {
                        uint32_t B[8];
                        const uint32_t v = va + pp * 1792 + (pp == 16 || (pp >= 9 && kg0 + 2 * pp >= 32) ? Y_VOWN - 32 * 896 : 0);
                        ldsm4t(v, B); ldsm4t(v + 256, B + 4);
                        float e[8];
                        const float bias = __uint_as_float((pp < pmin ? 0xFF800000u : 0u) | ((pp < 2 ? B[0] : pk[pp & 1]) & p.zero));
#pragma unroll
                        for (int i = 0; i < 8; i++) e[i] = ex2(fmaf(s[8 * pp + i], CS, ((i & 2) ? nb : na) + bias));
                        const uint32_t p0 = pack2(e[0], e[1]), p1 = pack2(e[2], e[3]), p2 = pack2(e[4], e[5]), p3 = pack2(e[6], e[7]);
                        pk[pp & 1] = p3;
                        mma16816(rs, p0, p1, p2, p3, 0x3F803F80u, 0x3F803F80u);
#pragma unroll
                        for (int g = 0; g < 4; g++) mma16816(o + 4 * g, p0, p1, p2, p3, B[2 * g], B[2 * g + 1]);
                    }
                    PROFC(9 + 3 * hf);
                    const float ia = rcp(rs[0]), ib = rcp(rs[2]);
                    uint32_t* og = act + RB_O + hf * 14336 + (7 * j + 3 * w) * 256 + wi * 64 + lane;
#pragma unroll
                    for (int g = 0; g < 4; g++) {
                        if ((g == 3 - 3 * w) ? ((q >> 1) == w) : true) {
                            og[g * 256] = pack2(o[4 * g] * ia, o[4 * g + 1] * ia);
                            og[g * 256 + 32] = pack2(o[4 * g + 2] * ib, o[4 * g + 3] * ib);
                        }
                    }
                    warp_arrive(BAR(B_PUB + 2 + hf));
                    PROFC(10 + 3 * hf);
                }
            }
        }
        uint32_t x1p[14];
        COORDS
        constexpr uint64_t DT = dconst(1024, 128, 0);
        const int tile = opaque((lds1(sb + M_EPOCH) & 1) * 2 + w);
        if (RUN(4)) {
            float ac[28];
            const uint32_t ad = mkdesc(sb + (w ? OFF_Y + HALF : OFF_X), DT), bd = mkdesc(sb + OFF_X + HALF, DB128) + kh;
            WAIT(B_WOFULL, 0);
            WAIT(B_MOD1, 1);
            WAIT(B_GFULL + w, 0);
            PROFC(28);
            reg_def<28>(ac);
#pragma unroll 1
            for (int u = 0; u < 4; u++) {
                if (u == 2) WAIT(B_XFULL + 2 + w, 1);
                WG_FENCE();
#pragma unroll
                for (int i = 0; i < 7; i++) wgmma_ss_56<DT, DB128>(ac, ad + (7 * u + i) * 128, bd + (7 * u + i) * 128, (u | i) != 0);
            }
            WG_COMMIT();
            WG_WAIT(0);
            reg_fence<28>(ac);
            PROFC(14);
            __syncwarp();
            if (lane < 3) mbar_arrive(BAR(B_EMPTY + 4 - w + lane));
            if (lane < 3 && w == 0) mbar_arrive(BAR(B_EMPTY + lane));
            float ds[4] = {}, da[4] = {}, db[4] = {};
            uint32_t* xo = act + RB_X1 + tile * 14336 + 7 * j * 256 + wi * 64 + lane;
#pragma unroll
            for (int g = 0; g < 7; g++) {
                const float2 ga = *(const float2*)(smem + M_G + (8 * g + 2 * q) * 4);
                x1p[2 * g] = pack2(fmaf(ga.x, ac[4 * g], bf_lo(xr[2 * g])), fmaf(ga.y, ac[4 * g + 1], bf_hi(xr[2 * g])));
                x1p[2 * g + 1] = pack2(fmaf(ga.x, ac[4 * g + 2], bf_lo(xr[2 * g + 1])), fmaf(ga.y, ac[4 * g + 3], bf_hi(xr[2 * g + 1])));
                st_relaxed(xo + g * 256, nz(x1p[2 * g])); st_relaxed(xo + g * 256 + 32, nz(x1p[2 * g + 1]));
                mma1688(ds, x1p[2 * g], x1p[2 * g + 1], 0x3F803F80u);
                mma1688(da, x1p[2 * g], x1p[2 * g + 1], x1p[2 * g]);
                mma1688(db, x1p[2 * g], x1p[2 * g + 1], x1p[2 * g + 1]);
            }
            const int src = (lane & ~3) | (lr >> 1);
            const float qa = __shfl_sync(~0u, (lr & 1) ? da[1] : da[0], src), qb = __shfl_sync(~0u, (lr & 1) ? db[3] : db[2], src);
            const float kk = (q & 1) ? ((q & 2) ? qb : qa) : ((q & 2) ? ds[2] : ds[0]);
            st_relaxed(act + RB_ST + ((tile * 8 + j) * 64 + 16 * wi + lr + 4 * (q & 2)) * 2 + (q & 1), nz(__float_as_uint(kk)));
            __syncwarp();
            if (lane < 2) mbar_arrive(BAR(B_PUB + 4 + w));
        } else reg_def<14>(x1p);
        PROFC(15);
        uint32_t h2a[32], h2b[24];
        {
            const int fa = pass_f(fs, 0), fb = pass_f(fs, 1), fc = pass_f(fs, 2);
            uint32_t* h2g = act + RB_H2 + (8 * w + 2 * wi) * 32 + lane;
            const uint32_t a0 = mkdesc(sb + OFF_Y + w * HALF, DT);
            if (RUN(3)) {
                uint32_t ra2, na2, rb2, nb2;
                {
                    const uint32_t* sg = act + RB_ST + ((tile * 8 + 2 * q) * 64 + 16 * wi + lr) * 2;
                    uint2 u[4];
                    WAIT(B_GFULL + 2 + w, 0);
                    PROFC(16);
#pragma unroll
                    for (int i = 0; i < 4; i++) { const float2 v = lds2f(sb + OFF_X + X_STAT + w * 49152 + ((2 * q + (i >> 1)) * 64 + 16 * wi + lr + 8 * (i & 1)) * 8); u[i] = make_uint2(__float_as_uint(v.x), __float_as_uint(v.y)); }
                    while (__any_sync(~0u, min(min(min(u[0].x, u[0].y), min(u[1].x, u[1].y)), min(min(u[2].x, u[2].y), min(u[3].x, u[3].y))) < 1u - sc)) {
#pragma unroll
                        for (int i = 0; i < 4; i++) u[i] = ld_relaxed2(sg + (i >> 1) * 128 + (i & 1) * 16);
                    }
                    warp_arrive(BAR(B_EMPTY + 3 + 3 * w));
                    float v[4] = {__uint_as_float(u[0].x) + __uint_as_float(u[2].x), __uint_as_float(u[0].y) + __uint_as_float(u[2].y),
                                  __uint_as_float(u[1].x) + __uint_as_float(u[3].x), __uint_as_float(u[1].y) + __uint_as_float(u[3].y)};
#pragma unroll
                    for (int i = 0; i < 4; i++) { v[i] += __shfl_xor_sync(~0u, v[i], 1); v[i] += __shfl_xor_sync(~0u, v[i], 2); }
                    ln_coeffs(v[0] * (1.f / DM), v[1] * (1.f / DM), ra2, na2);
                    ln_coeffs(v[2] * (1.f / DM), v[3] * (1.f / DM), rb2, nb2);
                }
                const uint32_t ha = sb + OFF_Y + w * HALF + (lane >> 4) * 1024 + (2 * wi + ((lane >> 3) & 1)) * 128 + (lane & 7) * 16;
                const uint32_t sta = sb + M_ST + q * 16;
                const uint32_t* xg = act + RB_X1 + tile * 14336 + (lane >> 4) * 256 + wi * 64 + (lane & 15) * 4;
                uint32_t x[8];
                const uint32_t xs = sb + OFF_Y + w * HALF + (lane >> 4) * 1024 + wi * 256 + (lane & 15) * 16;
                uint4 st[2];
                auto load = [&](int s) {
                    if (s == 4) mbar_wait_c(BAR(B_XFULL + 4 + w), 1);
                    ldsm4(ha + s * 4096, x); ldsm4(ha + s * 4096 + 2048, x + 4);
                    st[0] = lds4(sta + s * 128); st[1] = lds4(sta + s * 128 + 64);
                };
                auto prep = [&](int s, uint32_t* f) {
                    if (__any_sync(~0u, min(min(min(x[0], x[1]), min(x[2], x[3])), min(min(x[4], x[5]), min(x[6], x[7]))) < 1u - sc)) {
                        WG_WAIT(0);
                        x1_fix(xg, xs, s);
                        ldsm4(ha + s * 4096, x); ldsm4(ha + s * 4096 + 2048, x + 4);
                    }
#pragma unroll
                    for (int i = 0; i < 2; i++) {
                        f[4 * i] = hfma2(hfma2(x[4 * i], ra2, na2), st[i].x, st[i].y); f[4 * i + 1] = hfma2(hfma2(x[4 * i + 1], rb2, nb2), st[i].x, st[i].y);
                        f[4 * i + 2] = hfma2(hfma2(x[4 * i + 2], ra2, na2), st[i].z, st[i].w); f[4 * i + 3] = hfma2(hfma2(x[4 * i + 3], rb2, nb2), st[i].z, st[i].w);
                    }
                    if (s < 13) load(s + 1);
                    stsm4(ha + s * 4096, f[0], f[1], f[2], f[3]); stsm4(ha + s * 4096 + 2048, f[4], f[5], f[6], f[7]);
                };
                float ac[128];
                uint32_t fr[3][8];
                uint64_t bd = (DB128 & ~0xFFFFFFFFull) | mkdesc(sb, DB128);
                reg_def<128>(ac);
                load(0);
                prep(0, fr[0]);
                PROFC(17);
#pragma unroll
                for (int s = 0; s < 14; s++) {
                    const uint32_t* f = fr[s % 3];
                    WAIT(B_FULL + g1_slot(s), s >= 7);
                    WG_FENCE();
                    wgmma_rl_256(ac, f[0], f[1], f[2], f[3], bd, s != 0);
                    wgmma_rl_256(ac, f[4], f[5], f[6], f[7], bd + 128, 1);
                    bd += s == 6 ? p.zero - 6 * 1024ull : 1024;
                    WG_COMMIT();
                    if (s < 13) prep(s + 1, fr[(s + 1) % 3]);
                    if (s > 0) { WG_WAIT(1); warp_arrive(BAR(B_EMPTY + g1_slot(s - 1))); }
                }
                fence_async_smem();
                PROFC(18);
                WG_WAIT(0);
                reg_fence<128>(ac);
                warp_arrive(BAR(B_EMPTY + 6));
#pragma unroll
                for (int g = 0; g < 16; g++) {
                    h2a[2 * g] = hmul2(pack2_relu(ac[4 * g], ac[4 * g + 1]), pack2(ac[64 + 4 * g], ac[64 + 4 * g + 1]));
                    h2a[2 * g + 1] = hmul2(pack2_relu(ac[4 * g + 2], ac[4 * g + 3]), pack2(ac[64 + 4 * g + 2], ac[64 + 4 * g + 3]));
                }
                bar_sync(1 + w, 128);
            } else reg_def<32>(h2a);
            PROFC(19);
            if (RUN(5)) {
                float ac[64];
                reg_def<64>(ac);
                const uint32_t bx = mkdesc(sb, dconst(8192, 1024, 1));
#pragma unroll kB
                for (int s = 0; s < 7; s++) {
                    WAIT(B_FULL + s, 0);
                    const uint32_t ad = a0 + s * 512, bd = bx + (slot_off(s) >> 4);
                    WG_FENCE();
#pragma unroll
                    for (int k = 0; k < 4; k++) wgmma_ss_128<DT, DB128>(ac, ad + k * 128, bd + k * 128, (s | k) != 0);
                    WG_COMMIT();
                    if (s == 1) {
#pragma unroll
                        for (int g = 0; g < 16; g++) { h2g[(fa / 8 + g) * 512] = h2a[2 * g]; h2g[(fa / 8 + g) * 512 + 32] = h2a[2 * g + 1]; }
                        warp_arrive(BAR(B_PUB + 6));
                    }
                    if (s > 0) { WG_WAIT(1); warp_arrive(BAR(B_EMPTY + s - 1)); }
                }
                WG_WAIT(0);
                reg_fence<64>(ac);
                warp_arrive(BAR(B_EMPTY + 6));
#pragma unroll
                for (int g = 0; g < 8; g++) {
                    h2b[2 * g] = hmul2(pack2_relu(ac[4 * g], ac[4 * g + 1]), pack2(ac[32 + 4 * g], ac[32 + 4 * g + 1]));
                    h2b[2 * g + 1] = hmul2(pack2_relu(ac[4 * g + 2], ac[4 * g + 3]), pack2(ac[32 + 4 * g + 2], ac[32 + 4 * g + 3]));
                }
            } else reg_def<16>(h2b);
            PROFC(27);
            if (RUN(6)) {
                float ac[32];
                reg_def<32>(ac);
                const uint32_t bx = mkdesc(sb, dconst(4096, 512, 2));
#pragma unroll kC
                for (int s = 0; s < 7; s++) {
                    WAIT(B_FULL + s, 1);
                    const uint32_t ad = a0 + s * 512, bd = bx + (slot_off(s) >> 4);
                    WG_FENCE();
#pragma unroll
                    for (int k = 0; k < 4; k++) wgmma_ss_64<DT, dconst(4096, 512, 2)>(ac, ad + k * 128, bd + k * 64, (s | k) != 0);
                    WG_COMMIT();
                    if (s == 1) {
#pragma unroll
                        for (int g = 0; g < 8; g++) { h2g[(fb / 8 + g) * 512] = h2b[2 * g]; h2g[(fb / 8 + g) * 512 + 32] = h2b[2 * g + 1]; }
                        warp_arrive(BAR(B_PUB + 7));
                    }
                    if (s > 0) { WG_WAIT(1); warp_arrive(BAR(B_EMPTY + s - 1)); }
                }
                WG_WAIT(0);
                reg_fence<32>(ac);
                __syncwarp();
                if (lane < 6) mbar_arrive(BAR(B_EMPTY + 6 + lane));
                PROFC(20);
#pragma unroll
                for (int g = 0; g < 4; g++) {
                    h2b[16 + 2 * g] = hmul2(pack2_relu(ac[4 * g], ac[4 * g + 1]), pack2(ac[16 + 4 * g], ac[16 + 4 * g + 1]));
                    h2b[16 + 2 * g + 1] = hmul2(pack2_relu(ac[4 * g + 2], ac[4 * g + 3]), pack2(ac[16 + 4 * g + 2], ac[16 + 4 * g + 3]));
                    h2g[(fc / 8 + g) * 512] = h2b[16 + 2 * g]; h2g[(fc / 8 + g) * 512 + 32] = h2b[16 + 2 * g + 1];
                }
                warp_arrive(BAR(B_PUB + 8));
                asm volatile("barrier.cluster.wait.aligned;" ::: "memory");
                if (lane == 0 && !sc) {
                    uint32_t rb;
                    asm volatile("mapa.shared::cluster.u32 %0, %1, %2;" : "=r"(rb) : "r"(BAR(B_PEER)), "r"(kh ^ 1));
                    asm volatile("mbarrier.arrive.relaxed.cluster.shared::cluster.b64 _, [%0];" ::"r"(rb) : "memory");
                }
            } else reg_def<8>(h2b + 16);
        }
        PROFC(21);
        if (RUN(7)) {
            float ac[56];
            reg_def<56>(ac);
            constexpr uint64_t DAN = dconst(2048, 128, 0);
            constexpr uint64_t DW = dconst(128, 512, 0);
            const uint32_t bx = mkdesc(sb, DW);
#pragma unroll
            for (int e = 0; e < 4; e++) {
                WAIT(B_FULL + e, 0);
                const uint64_t bd = ((DW & ~0xFFFFFFFFull) | bx) + (slot_off(e) >> 4);
                const uint32_t* hh = e < 2 ? h2a + 16 * e : h2b + 16 * (e - 2);
                WG_FENCE();
#pragma unroll
                for (int k = 0; k < (e < 3 ? 4 : 2); k++) wgmma_rl_112(ac, hh[4 * k], hh[4 * k + 1], hh[4 * k + 2], hh[4 * k + 3], bd + (k >> 1) * 512 + (k & 1) * 16, (e | k) != 0);
                WG_COMMIT();
                if (e > 0) { WG_WAIT(1); warp_arrive(BAR(B_EMPTY + e - 1)); }
            }
            PROFC(22);
            uint32_t ad = mkdesc(sb + 4 * 16384 + 8192 + w * 1024, DAN), bd = bx + 4 * 1024, fb_ = BAR(B_FULL + 4), eb_ = BAR(B_EMPTY + 3), par = sc;
#pragma unroll 1
            for (int e = 4; e < 25; e++) {
                mbar_wait_c(fb_, par);
                WG_FENCE();
                wgmma_ss_112<DAN, DW>(ac, ad, bd, 1);
                wgmma_ss_112<DAN, DW>(ac, ad + 256, bd + 16, 1);
                WG_COMMIT();
                WG_WAIT(1);
                warp_arrive(eb_);
                eb_ = fb_ + 8 * (B_EMPTY - B_FULL);
                ad += 1024; bd += 1024; fb_ += 8;
                if (e == 11 || e == 23) { ad -= 12 * 1024; bd -= 12 * 1024; fb_ -= 96; par = (par ^ 1) | sc; }
            }
            mbar_wait_cluster(BAR(B_PEER), sc);
            WG_WAIT(0);
            reg_fence<56>(ac);
            PROFC(24);
            uint32_t rdst, rbar;
            asm volatile("mapa.shared::cluster.u32 %0, %1, %2;" : "=r"(rdst) : "r"(sb + OFF_Y + (5 + w) * 16384 + t * 16), "r"(kh ^ 1 ^ sc));
            asm volatile("mapa.shared::cluster.u32 %0, %1, %2;" : "=r"(rbar) : "r"(BAR(B_XCH + w)), "r"(kh ^ 1 ^ sc));
#pragma unroll
            for (int g = 0; g < 7; g++) {
                const float v0 = ac[28 + 4 * g + 0], v1 = ac[28 + 4 * g + 1];
                const float v2 = ac[28 + 4 * g + 2], v3 = ac[28 + 4 * g + 3];
                if (!sc) asm volatile("st.async.shared::cluster.mbarrier::complete_tx::bytes.v4.f32 [%0], {%1,%2,%3,%4}, [%5];"
                             ::"r"(rdst + g * 2048), "f"(v0), "f"(v1), "f"(v2), "f"(v3), "r"(rbar) : "memory");
            }
            mbar_wait_cluster(BAR(B_XCH + w), sc);
            PROFC(25);
            bf16* og = (sc ? (bf16*)act : p.out + (size_t)128 * r * DM) + (size_t)ra * DM + 56 * j + 2 * q;
#pragma unroll
            for (int g = 0; g < 7; g++) {
                const uint4 rv = *(const uint4*)(smem + OFF_Y + (5 + w) * 16384 + t * 16 + g * 2048);
                const float2 gb = *(const float2*)(smem + M_G + 224 + (8 * g + 2 * q) * 4);
                const float v0 = ac[4 * g + 0] + __uint_as_float(rv.x), v1 = ac[4 * g + 1] + __uint_as_float(rv.y);
                const float v2 = ac[4 * g + 2] + __uint_as_float(rv.z), v3 = ac[4 * g + 3] + __uint_as_float(rv.w);
                *(uint32_t*)(og + 8 * g) = pack2(fmaf(gb.x, v0, bf_lo(x1p[2 * g])), fmaf(gb.y, v1, bf_hi(x1p[2 * g])));
                *(uint32_t*)(og + 8 * DM + 8 * g) = pack2(fmaf(gb.x, v2, bf_lo(x1p[2 * g + 1])), fmaf(gb.y, v3, bf_hi(x1p[2 * g + 1])));
            }
        }
        PROFC(26);
        bar_sync(1 + w, 128);
        if (wi == 0) warp_arrive(BAR(B_DONE));
        return;
    }
    helper_late(p, r, j, warp PROF_ARGS);
}

#undef act
typedef CUresult (*EncodeFn)(CUtensorMap*, CUtensorMapDataType, cuuint32_t, void*, const cuuint64_t*, const cuuint64_t*, const cuuint32_t*,
                             const cuuint32_t*, CUtensorMapInterleave, CUtensorMapSwizzle, CUtensorMapL2promotion, CUtensorMapFloatOOBfill);

static void make_map(EncodeFn fn, CUtensorMap* m, const void* ptr, uint64_t d0, uint64_t d1, uint64_t d2, uint64_t s1, uint64_t s2,
                     uint32_t b0, uint32_t b1, uint32_t b2, CUtensorMapSwizzle sw) {
    cuuint64_t dims[3] = {d0, d1, d2}, strides[2] = {s1, s2};
    cuuint32_t box[3] = {b0, b1, b2}, es[3] = {1, 1, 1};
    CUresult rc = fn(m, CU_TENSOR_MAP_DATA_TYPE_BFLOAT16, 3, (void*)ptr, dims, strides, box, es, CU_TENSOR_MAP_INTERLEAVE_NONE, sw,
                     CU_TENSOR_MAP_L2_PROMOTION_L2_128B, CU_TENSOR_MAP_FLOAT_OOB_FILL_NONE);
    (void)rc;
}

extern "C" void kernel_launch(void* const* d_in, const int* in_sizes, int n_in, void* d_out, int out_size) {
    (void)in_sizes; (void)n_in; (void)out_size;
    static EncodeFn fn = nullptr;
    static uint32_t* act_base = nullptr;
    if (!fn) {
        cudaDriverEntryPointQueryResult st;
        cudaGetDriverEntryPoint("cuTensorMapEncodeTiled", (void**)&fn, cudaEnableDefault, &st);
        void* a = nullptr;
        cudaGetSymbolAddress(&a, g_act);
        act_base = (uint32_t*)(((uintptr_t)a + 0xFFFFF) & ~(uintptr_t)0xFFFFF);
        cudaFuncSetAttribute(fused_block_kernel, cudaFuncAttributeMaxDynamicSharedMemorySize, SMEM_BYTES);
    }
    Params p;
    p.x = (const bf16*)d_in[0];
    const bf16* wqkv = (const bf16*)d_in[1];
    p.wqkv = wqkv;
    p.wop = (const bf16*)d_in[2];
    p.wg = (const bf16*)d_in[4];
    p.wu = (const bf16*)d_in[5];
    p.wd = (const bf16*)d_in[6];
    p.c = (const bf16*)d_in[7];
    p.wmod = (const bf16*)d_in[8];
    p.out = (bf16*)d_out;
    p.zero = 0;
    p.actb = act_base;
    make_map(fn, &p.wm, p.wmod, 2688, 448, 1, 5376, 5376 * 448, 16, 224, 1, CU_TENSOR_MAP_SWIZZLE_NONE);
    make_map(fn, &p.xm, p.x, 448, 2048, 1, 896, 896 * 2048, 64, 128, 1, CU_TENSOR_MAP_SWIZZLE_128B);
    make_map(fn, &p.qkv, wqkv, 1344, 448, 1, 2688, 2688 * 448, 64, 224, 1, CU_TENSOR_MAP_SWIZZLE_128B);
    make_map(fn, &p.wo, p.wop, 448, 448, 1, 896, 896 * 448, 64, 224, 1, CU_TENSOR_MAP_SWIZZLE_128B);
    make_map(fn, &p.ga, p.wg, 64, 448, 28, 3584, 128, 64, 32, 2, CU_TENSOR_MAP_SWIZZLE_128B);
    make_map(fn, &p.ua, p.wu, 64, 448, 28, 3584, 128, 64, 32, 2, CU_TENSOR_MAP_SWIZZLE_128B);
    make_map(fn, &p.gb, p.wg, 64, 448, 28, 3584, 128, 64, 64, 1, CU_TENSOR_MAP_SWIZZLE_128B);
    make_map(fn, &p.ub, p.wu, 64, 448, 28, 3584, 128, 64, 64, 1, CU_TENSOR_MAP_SWIZZLE_128B);
    make_map(fn, &p.gc, p.wg, 32, 448, 56, 3584, 64, 32, 64, 1, CU_TENSOR_MAP_SWIZZLE_64B);
    make_map(fn, &p.uc, p.wu, 32, 448, 56, 3584, 64, 32, 64, 1, CU_TENSOR_MAP_SWIZZLE_64B);
    make_map(fn, &p.dn, p.wd, 8, 1792, 56, 896, 16, 8, 32, 7, CU_TENSOR_MAP_SWIZZLE_NONE);
    fused_block_kernel<<<GRID, 384, SMEM_BYTES>>>(p);
}
```

```cpp
#include <cuda_runtime.h>
#include <cuda_bf16.h>
#include <cuda.h>
#include <stdint.h>

typedef __nv_bfloat16 bf16;

__device__ __forceinline__ void wgmma_rl_56(float* d, uint32_t a0, uint32_t a1, uint32_t a2, uint32_t a3, uint64_t db, int sd) {
  asm volatile("{\n.reg .pred p;\nsetp.ne.b32 p, %33, 0;\n"
    "wgmma.mma_async.sync.aligned.m64n56k16.f32.bf16.bf16 {%0,%1,%2,%3,%4,%5,%6,%7,%8,%9,%10,%11,%12,%13,%14,%15,%16,%17,%18,%19,%20,%21,%22,%23,%24,%25,%26,%27}, {%28,%29,%30,%31}, %32, p, 1, 1, 1;\n}\n"
    : "+f"(d[0]),"+f"(d[1]),"+f"(d[2]),"+f"(d[3]),"+f"(d[4]),"+f"(d[5]),"+f"(d[6]),"+f"(d[7]),"+f"(d[8]),"+f"(d[9]),"+f"(d[10]),"+f"(d[11]),"+f"(d[12]),"+f"(d[13]),"+f"(d[14]),"+f"(d[15]),"+f"(d[16]),"+f"(d[17]),"+f"(d[18]),"+f"(d[19]),"+f"(d[20]),"+f"(d[21]),"+f"(d[22]),"+f"(d[23]),"+f"(d[24]),"+f"(d[25]),"+f"(d[26]),"+f"(d[27])
    : "r"(a0), "r"(a1), "r"(a2), "r"(a3), "l"(db), "r"(sd));
}
template<uint64_t CA, uint64_t CB> __device__ __forceinline__ void wgmma_ss_56(float* d, uint32_t da, uint32_t db, int sd) {
  asm volatile("{\n.reg .pred p;\n.reg .b64 a, b;\nsetp.ne.b32 p, %30, 0;\nmov.b64 a, {%28, %31};\nmov.b64 b, {%29, %32};\n"
    "wgmma.mma_async.sync.aligned.m64n56k16.f32.bf16.bf16 {%0,%1,%2,%3,%4,%5,%6,%7,%8,%9,%10,%11,%12,%13,%14,%15,%16,%17,%18,%19,%20,%21,%22,%23,%24,%25,%26,%27}, a, b, p, 1, 1, 0, 1;\n}\n"
    : "+f"(d[0]),"+f"(d[1]),"+f"(d[2]),"+f"(d[3]),"+f"(d[4]),"+f"(d[5]),"+f"(d[6]),"+f"(d[7]),"+f"(d[8]),"+f"(d[9]),"+f"(d[10]),"+f"(d[11]),"+f"(d[12]),"+f"(d[13]),"+f"(d[14]),"+f"(d[15]),"+f"(d[16]),"+f"(d[17]),"+f"(d[18]),"+f"(d[19]),"+f"(d[20]),"+f"(d[21]),"+f"(d[22]),"+f"(d[23]),"+f"(d[24]),"+f"(d[25]),"+f"(d[26]),"+f"(d[27])
    : "r"(da), "r"(db), "r"(sd), "n"((uint32_t)(CA >> 32)), "n"((uint32_t)(CB >> 32)));
}
__device__ __forceinline__ void wgmma_rl_256(float* d, uint32_t a0, uint32_t a1, uint32_t a2, uint32_t a3, uint64_t db, int sd) {
  asm volatile("{\n.reg .pred p;\nsetp.ne.b32 p, %133, 0;\n"
    "wgmma.mma_async.sync.aligned.m64n256k16.f32.bf16.bf16 {%0,%1,%2,%3,%4,%5,%6,%7,%8,%9,%10,%11,%12,%13,%14,%15,%16,%17,%18,%19,%20,%21,%22,%23,%24,%25,%26,%27,%28,%29,%30,%31,%32,%33,%34,%35,%36,%37,%38,%39,%40,%41,%42,%43,%44,%45,%46,%47,%48,%49,%50,%51,%52,%53,%54,%55,%56,%57,%58,%59,%60,%61,%62,%63,%64,%65,%66,%67,%68,%69,%70,%71,%72,%73,%74,%75,%76,%77,%78,%79,%80,%81,%82,%83,%84,%85,%86,%87,%88,%89,%90,%91,%92,%93,%94,%95,%96,%97,%98,%99,%100,%101,%102,%103,%104,%105,%106,%107,%108,%109,%110,%111,%112,%113,%114,%115,%116,%117,%118,%119,%120,%121,%122,%123,%124,%125,%126,%127}, {%128,%129,%130,%131}, %132, p, 1, 1, 1;\n}\n"
    : "+f"(d[0]),"+f"(d[1]),"+f"(d[2]),"+f"(d[3]),"+f"(d[4]),"+f"(d[5]),"+f"(d[6]),"+f"(d[7]),"+f"(d[8]),"+f"(d[9]),"+f"(d[10]),"+f"(d[11]),"+f"(d[12]),"+f"(d[13]),"+f"(d[14]),"+f"(d[15]),"+f"(d[16]),"+f"(d[17]),"+f"(d[18]),"+f"(d[19]),"+f"(d[20]),"+f"(d[21]),"+f"(d[22]),"+f"(d[23]),"+f"(d[24]),"+f"(d[25]),"+f"(d[26]),"+f"(d[27]),"+f"(d[28]),"+f"(d[29]),"+f"(d[30]),"+f"(d[31]),"+f"(d[32]),"+f"(d[33]),"+f"(d[34]),"+f"(d[35]),"+f"(d[36]),"+f"(d[37]),"+f"(d[38]),"+f"(d[39]),"+f"(d[40]),"+f"(d[41]),"+f"(d[42]),"+f"(d[43]),"+f"(d[44]),"+f"(d[45]),"+f"(d[46]),"+f"(d[47]),"+f"(d[48]),"+f"(d[49]),"+f"(d[50]),"+f"(d[51]),"+f"(d[52]),"+f"(d[53]),"+f"(d[54]),"+f"(d[55]),"+f"(d[56]),"+f"(d[57]),"+f"(d[58]),"+f"(d[59]),"+f"(d[60]),"+f"(d[61]),"+f"(d[62]),"+f"(d[63]),"+f"(d[64]),"+f"(d[65]),"+f"(d[66]),"+f"(d[67]),"+f"(d[68]),"+f"(d[69]),"+f"(d[70]),"+f"(d[71]),"+f"(d[72]),"+f"(d[73]),"+f"(d[74]),"+f"(d[75]),"+f"(d[76]),"+f"(d[77]),"+f"(d[78]),"+f"(d[79]),"+f"(d[80]),"+f"(d[81]),"+f"(d[82]),"+f"(d[83]),"+f"(d[84]),"+f"(d[85]),"+f"(d[86]),"+f"(d[87]),"+f"(d[88]),"+f"(d[89]),"+f"(d[90]),"+f"(d[91]),"+f"(d[92]),"+f"(d[93]),"+f"(d[94]),"+f"(d[95]),"+f"(d[96]),"+f"(d[97]),"+f"(d[98]),"+f"(d[99]),"+f"(d[100]),"+f"(d[101]),"+f"(d[102]),"+f"(d[103]),"+f"(d[104]),"+f"(d[105]),"+f"(d[106]),"+f"(d[107]),"+f"(d[108]),"+f"(d[109]),"+f"(d[110]),"+f"(d[111]),"+f"(d[112]),"+f"(d[113]),"+f"(d[114]),"+f"(d[115]),"+f"(d[116]),"+f"(d[117]),"+f"(d[118]),"+f"(d[119]),"+f"(d[120]),"+f"(d[121]),"+f"(d[122]),"+f"(d[123]),"+f"(d[124]),"+f"(d[125]),"+f"(d[126]),"+f"(d[127])
    : "r"(a0), "r"(a1), "r"(a2), "r"(a3), "l"(db), "r"(sd));
}
template<uint64_t CA, uint64_t CB> __device__ __forceinline__ void wgmma_ss_128(float* d, uint32_t da, uint32_t db, int sd) {
  asm volatile("{\n.reg .pred p;\n.reg .b64 a, b;\nsetp.ne.b32 p, %66, 0;\nmov.b64 a, {%64, %67};\nmov.b64 b, {%65, %68};\n"
    "wgmma.mma_async.sync.aligned.m64n128k16.f32.bf16.bf16 {%0,%1,%2,%3,%4,%5,%6,%7,%8,%9,%10,%11,%12,%13,%14,%15,%16,%17,%18,%19,%20,%21,%22,%23,%24,%25,%26,%27,%28,%29,%30,%31,%32,%33,%34,%35,%36,%37,%38,%39,%40,%41,%42,%43,%44,%45,%46,%47,%48,%49,%50,%51,%52,%53,%54,%55,%56,%57,%58,%59,%60,%61,%62,%63}, a, b, p, 1, 1, 0, 1;\n}\n"
    : "+f"(d[0]),"+f"(d[1]),"+f"(d[2]),"+f"(d[3]),"+f"(d[4]),"+f"(d[5]),"+f"(d[6]),"+f"(d[7]),"+f"(d[8]),"+f"(d[9]),"+f"(d[10]),"+f"(d[11]),"+f"(d[12]),"+f"(d[13]),"+f"(d[14]),"+f"(d[15]),"+f"(d[16]),"+f"(d[17]),"+f"(d[18]),"+f"(d[19]),"+f"(d[20]),"+f"(d[21]),"+f"(d[22]),"+f"(d[23]),"+f"(d[24]),"+f"(d[25]),"+f"(d[26]),"+f"(d[27]),"+f"(d[28]),"+f"(d[29]),"+f"(d[30]),"+f"(d[31]),"+f"(d[32]),"+f"(d[33]),"+f"(d[34]),"+f"(d[35]),"+f"(d[36]),"+f"(d[37]),"+f"(d[38]),"+f"(d[39]),"+f"(d[40]),"+f"(d[41]),"+f"(d[42]),"+f"(d[43]),"+f"(d[44]),"+f"(d[45]),"+f"(d[46]),"+f"(d[47]),"+f"(d[48]),"+f"(d[49]),"+f"(d[50]),"+f"(d[51]),"+f"(d[52]),"+f"(d[53]),"+f"(d[54]),"+f"(d[55]),"+f"(d[56]),"+f"(d[57]),"+f"(d[58]),"+f"(d[59]),"+f"(d[60]),"+f"(d[61]),"+f"(d[62]),"+f"(d[63])
    : "r"(da), "r"(db), "r"(sd), "n"((uint32_t)(CA >> 32)), "n"((uint32_t)(CB >> 32)));
}
template<uint64_t CA, uint64_t CB> __device__ __forceinline__ void wgmma_ss_64(float* d, uint32_t da, uint32_t db, int sd) {
  asm volatile("{\n.reg .pred p;\n.reg .b64 a, b;\nsetp.ne.b32 p, %34, 0;\nmov.b64 a, {%32, %35};\nmov.b64 b, {%33, %36};\n"
    "wgmma.mma_async.sync.aligned.m64n64k16.f32.bf16.bf16 {%0,%1,%2,%3,%4,%5,%6,%7,%8,%9,%10,%11,%12,%13,%14,%15,%16,%17,%18,%19,%20,%21,%22,%23,%24,%25,%26,%27,%28,%29,%30,%31}, a, b, p, 1, 1, 0, 1;\n}\n"
    : "+f"(d[0]),"+f"(d[1]),"+f"(d[2]),"+f"(d[3]),"+f"(d[4]),"+f"(d[5]),"+f"(d[6]),"+f"(d[7]),"+f"(d[8]),"+f"(d[9]),"+f"(d[10]),"+f"(d[11]),"+f"(d[12]),"+f"(d[13]),"+f"(d[14]),"+f"(d[15]),"+f"(d[16]),"+f"(d[17]),"+f"(d[18]),"+f"(d[19]),"+f"(d[20]),"+f"(d[21]),"+f"(d[22]),"+f"(d[23]),"+f"(d[24]),"+f"(d[25]),"+f"(d[26]),"+f"(d[27]),"+f"(d[28]),"+f"(d[29]),"+f"(d[30]),"+f"(d[31])
    : "r"(da), "r"(db), "r"(sd), "n"((uint32_t)(CA >> 32)), "n"((uint32_t)(CB >> 32)));
}
template<uint64_t CA, uint64_t CB> __device__ __forceinline__ void wgmma_ss_112(float* d, uint32_t da, uint32_t db, int sd) {
  asm volatile("{\n.reg .pred p;\n.reg .b64 a, b;\nsetp.ne.b32 p, %58, 0;\nmov.b64 a, {%56, %59};\nmov.b64 b, {%57, %60};\n"
    "wgmma.mma_async.sync.aligned.m64n112k16.f32.bf16.bf16 {%0,%1,%2,%3,%4,%5,%6,%7,%8,%9,%10,%11,%12,%13,%14,%15,%16,%17,%18,%19,%20,%21,%22,%23,%24,%25,%26,%27,%28,%29,%30,%31,%32,%33,%34,%35,%36,%37,%38,%39,%40,%41,%42,%43,%44,%45,%46,%47,%48,%49,%50,%51,%52,%53,%54,%55}, a, b, p, 1, 1, 0, 1;\n}\n"
    : "+f"(d[0]),"+f"(d[1]),"+f"(d[2]),"+f"(d[3]),"+f"(d[4]),"+f"(d[5]),"+f"(d[6]),"+f"(d[7]),"+f"(d[8]),"+f"(d[9]),"+f"(d[10]),"+f"(d[11]),"+f"(d[12]),"+f"(d[13]),"+f"(d[14]),"+f"(d[15]),"+f"(d[16]),"+f"(d[17]),"+f"(d[18]),"+f"(d[19]),"+f"(d[20]),"+f"(d[21]),"+f"(d[22]),"+f"(d[23]),"+f"(d[24]),"+f"(d[25]),"+f"(d[26]),"+f"(d[27]),"+f"(d[28]),"+f"(d[29]),"+f"(d[30]),"+f"(d[31]),"+f"(d[32]),"+f"(d[33]),"+f"(d[34]),"+f"(d[35]),"+f"(d[36]),"+f"(d[37]),"+f"(d[38]),"+f"(d[39]),"+f"(d[40]),"+f"(d[41]),"+f"(d[42]),"+f"(d[43]),"+f"(d[44]),"+f"(d[45]),"+f"(d[46]),"+f"(d[47]),"+f"(d[48]),"+f"(d[49]),"+f"(d[50]),"+f"(d[51]),"+f"(d[52]),"+f"(d[53]),"+f"(d[54]),"+f"(d[55])
    : "r"(da), "r"(db), "r"(sd), "n"((uint32_t)(CA >> 32)), "n"((uint32_t)(CB >> 32)));
}
__device__ __forceinline__ void wgmma_rl_112(float* d, uint32_t a0, uint32_t a1, uint32_t a2, uint32_t a3, uint64_t db, int sd) {
  asm volatile("{\n.reg .pred p;\nsetp.ne.b32 p, %61, 0;\n"
    "wgmma.mma_async.sync.aligned.m64n112k16.f32.bf16.bf16 {%0,%1,%2,%3,%4,%5,%6,%7,%8,%9,%10,%11,%12,%13,%14,%15,%16,%17,%18,%19,%20,%21,%22,%23,%24,%25,%26,%27,%28,%29,%30,%31,%32,%33,%34,%35,%36,%37,%38,%39,%40,%41,%42,%43,%44,%45,%46,%47,%48,%49,%50,%51,%52,%53,%54,%55}, {%56,%57,%58,%59}, %60, p, 1, 1, 1;\n}\n"
    : "+f"(d[0]),"+f"(d[1]),"+f"(d[2]),"+f"(d[3]),"+f"(d[4]),"+f"(d[5]),"+f"(d[6]),"+f"(d[7]),"+f"(d[8]),"+f"(d[9]),"+f"(d[10]),"+f"(d[11]),"+f"(d[12]),"+f"(d[13]),"+f"(d[14]),"+f"(d[15]),"+f"(d[16]),"+f"(d[17]),"+f"(d[18]),"+f"(d[19]),"+f"(d[20]),"+f"(d[21]),"+f"(d[22]),"+f"(d[23]),"+f"(d[24]),"+f"(d[25]),"+f"(d[26]),"+f"(d[27]),"+f"(d[28]),"+f"(d[29]),"+f"(d[30]),"+f"(d[31]),"+f"(d[32]),"+f"(d[33]),"+f"(d[34]),"+f"(d[35]),"+f"(d[36]),"+f"(d[37]),"+f"(d[38]),"+f"(d[39]),"+f"(d[40]),"+f"(d[41]),"+f"(d[42]),"+f"(d[43]),"+f"(d[44]),"+f"(d[45]),"+f"(d[46]),"+f"(d[47]),"+f"(d[48]),"+f"(d[49]),"+f"(d[50]),"+f"(d[51]),"+f"(d[52]),"+f"(d[53]),"+f"(d[54]),"+f"(d[55])
    : "r"(a0), "r"(a1), "r"(a2), "r"(a3), "l"(db), "r"(sd));
}

constexpr int DM = 448;
constexpr int NCTA = 128;
#define MAPPING 1
#define GRID 128
#define PINGPONG 0
#define WIN 6
#define WIN_END 25
#define UNR_B 1
#define UNR_C 1
constexpr int kB = UNR_B, kC = UNR_C;
#define LIKELY(x) __builtin_expect(!!(x), 1)
#define PACE 1
#define PACE_END 6
#define GEMV_AT 2
#define NPRE 14
#define MAP_S 4
constexpr int SPIN_LIMIT = 1 << 22;

constexpr uint32_t OFF_X = 0, OFF_Y = 114688, OFF_MISC = 229376, SMEM_BYTES = 232448;
constexpr uint32_t Y_VR = 0, Y_K = 28672, Y_KOWN = 57344, Y_VOWN = 71680, Y_Q = 86016;
constexpr uint32_t HALF = 57344;
constexpr uint32_t X_STAT = 49152;
constexpr uint32_t M_BAR = OFF_MISC;
constexpr uint32_t M_ST = OFF_MISC + 512;
constexpr uint32_t M_G = OFF_MISC + 2304;
constexpr uint32_t M_EPOCH = OFF_MISC + 3040;
enum { B_XFULL = 0, B_FULLK = 7, B_FULLV = 8, B_FULLQ, B_KRFULL, B_VRFULL, B_WOFULL, B_XCH, B_MOD1 = 15, B_FULL = 16, B_WMFULL = 30,
       B_EMPTY = 32, B_XFREE = B_EMPTY + 12, B_GEMV, B_PEER,
       B_PUB = 47,
       B_WMFREE = 56, B_HRDY, B_GFULL = B_HRDY + 3, B_DONE = 31, B_DUMMY = B_GEMV };

__device__ uint32_t g_ticket;
__device__ __align__(128) uint32_t g_mod[8 * 6 * DM];
__device__ __align__(128) uint32_t g_flag[144 * 128];
constexpr int RB_WORDS = 262144, RB_KV = 0, RB_O = 57344, RB_X1 = 86016, RB_H2 = 143360, RB_ST = 258048;
__device__ __align__(128) uint32_t g_act[18 * RB_WORDS];
__device__ __align__(128) uint32_t g_wd[56 * 4 * 1792];
#define PROFH(id)
#define PROFH1(id)
#define PROFC(id)

struct alignas(64) Params {
    CUtensorMap wm, xm, qkv, wo, ga, ua, gb, ub, gc, uc, dn;
    const bf16 *x, *c, *wqkv, *wmod, *wg, *wu, *wd, *wop;
    bf16* out;
    uint32_t* actb;
    uint32_t zero;
};

__device__ __forceinline__ void mbar_init(uint32_t bar, int cnt) { asm volatile("mbarrier.init.shared::cta.b64 [%0], %1;" ::"r"(bar), "r"(cnt) : "memory"); }
__device__ __forceinline__ void mbar_expect_tx(uint32_t bar, uint32_t bytes) { asm volatile("mbarrier.arrive.expect_tx.shared::cta.b64 _, [%0], %1;" ::"r"(bar), "r"(bytes) : "memory"); }
__device__ __forceinline__ void mbar_arrive(uint32_t bar) { asm volatile("mbarrier.arrive.shared::cta.b64 _, [%0];" ::"r"(bar) : "memory"); }
__device__ __forceinline__ void mbar_wait(uint32_t bar, uint32_t parity) {
    uint32_t ok; int n = 0;
    do {
        asm volatile("{\n.reg .pred p;\nmbarrier.try_wait.parity.shared::cta.b64 p, [%1], %2;\nselp.u32 %0, 1, 0, p;\n}" : "=r"(ok) : "r"(bar), "r"(parity) : "memory");
        if (++n > SPIN_LIMIT) __trap();
    } while (!ok);
}
__device__ __forceinline__ void mbar_wait_c(uint32_t bar, uint32_t parity) {
    asm volatile("{\n.reg .pred p;\nWL:\nmbarrier.try_wait.parity.shared::cta.b64 p, [%0], %1, 0x989680;\n@!p bra WL;\n}" ::"r"(bar), "r"(parity) : "memory");
}
__device__ __forceinline__ void mbar_wait_cluster(uint32_t bar, uint32_t parity) {
    asm volatile("{\n.reg .pred p;\nWL:\nmbarrier.try_wait.parity.acquire.cluster.shared::cta.b64 p, [%0], %1, 0x989680;\n@!p bra WL;\n}" ::"r"(bar), "r"(parity) : "memory");
}
__device__ __forceinline__ void warp_arrive(uint32_t bar) {
    __syncwarp();
    asm volatile("{\n.reg .pred p;\nelect.sync _|p, 0xffffffff;\n@p mbarrier.arrive.shared::cta.b64 _, [%0];\n}" ::"r"(bar) : "memory");
}
__device__ __forceinline__ int opaque(int v) { return __shfl_sync(~0u, v, 0); }
__device__ __forceinline__ int fresh_tid() { int v; asm volatile("mov.u32 %0, %%tid.x;" : "=r"(v)); return v; }
__device__ __forceinline__ void bar_sync(int id, int n) { asm volatile("bar.sync %0, %1;" ::"r"(id), "r"(n) : "memory"); }
__device__ __forceinline__ void bar_arrive(int id, int n) { asm volatile("bar.arrive %0, %1;" ::"r"(id), "r"(n) : "memory"); }
__device__ __forceinline__ void fence_async_smem() { asm volatile("fence.proxy.async.shared::cta;" ::: "memory"); }
__device__ __forceinline__ void fence_async_global() { asm volatile("fence.proxy.async.global;" ::: "memory"); }
__device__ __forceinline__ void fence_gpu() { asm volatile("fence.release.gpu;" ::: "memory"); }
__device__ __forceinline__ void tma3(uint32_t dst, const CUtensorMap* m, int c0, int c1, int c2, uint32_t bar) {
    asm volatile("cp.async.bulk.tensor.3d.shared::cluster.global.mbarrier::complete_tx::bytes [%0], [%1, {%3, %4, %5}], [%2];"
                 ::"r"(dst), "l"(m), "r"(bar), "r"(c0), "r"(c1), "r"(c2) : "memory");
}
__device__ __forceinline__ void bulk_load(uint32_t dst, const void* src, uint32_t bytes, uint32_t bar) {
    asm volatile("cp.async.bulk.shared::cluster.global.mbarrier::complete_tx::bytes [%0], [%1], %2, [%3];" ::"r"(dst), "l"(src), "r"(bytes), "r"(bar) : "memory");
}
__device__ __forceinline__ void expect_e(uint32_t bar, uint32_t bytes) {
    asm volatile("{\n.reg .pred p;\nelect.sync _|p, 0xffffffff;\n@p mbarrier.arrive.expect_tx.shared::cta.b64 _, [%0], %1;\n}" ::"r"(bar), "r"(bytes) : "memory");
}
__device__ __forceinline__ void tma3_e(uint32_t dst, const CUtensorMap* m, int c0, int c1, int c2, uint32_t bar) {
    asm volatile("{\n.reg .pred p;\nelect.sync _|p, 0xffffffff;\n@p cp.async.bulk.tensor.3d.shared::cluster.global.mbarrier::complete_tx::bytes [%0], [%1, {%3, %4, %5}], [%2];\n}"
                 ::"r"(dst), "l"(m), "r"(bar), "r"(c0), "r"(c1), "r"(c2) : "memory");
}
__device__ __forceinline__ void bulk_e(uint32_t dst, const void* src, uint32_t bytes, uint32_t bar) {
    asm volatile("{\n.reg .pred p;\nelect.sync _|p, 0xffffffff;\n@p cp.async.bulk.shared::cluster.global.mbarrier::complete_tx::bytes [%0], [%1], %2, [%3];\n}"
                 ::"r"(dst), "l"(src), "r"(bytes), "r"(bar) : "memory");
}
__device__ __forceinline__ void init_e(uint32_t bar, int cnt) {
    asm volatile("{\n.reg .pred p;\nelect.sync _|p, 0xffffffff;\n@p mbarrier.init.shared::cta.b64 [%0], %1;\n}" ::"r"(bar), "r"(cnt) : "memory");
}
__device__ __forceinline__ void l2_prefetch_e(const void* src, uint32_t bytes) {
    asm volatile("{\n.reg .pred p;\nelect.sync _|p, 0xffffffff;\n@p cp.async.bulk.prefetch.L2.global [%0], %1;\n}" ::"l"(src), "r"(bytes) : "memory");
}
__device__ __forceinline__ uint32_t ld_relaxed(const uint32_t* p) { uint32_t v; asm volatile("ld.relaxed.gpu.global.u32 %0, [%1];" : "=r"(v) : "l"(p) : "memory"); return v; }
__device__ __forceinline__ void st_relaxed(uint32_t* p, uint32_t v) { asm volatile("st.relaxed.gpu.global.u32 [%0], %1;" ::"l"(p), "r"(v) : "memory"); }
__device__ __forceinline__ uint4 ld_relaxed4(const uint4* p) { uint4 v; asm volatile("ld.relaxed.gpu.global.v4.u32 {%0,%1,%2,%3}, [%4];" : "=r"(v.x), "=r"(v.y), "=r"(v.z), "=r"(v.w) : "l"(p) : "memory"); return v; }
__device__ __forceinline__ void st_relaxed4(uint4* p, uint4 v) { asm volatile("st.relaxed.gpu.global.v4.u32 [%0], {%1,%2,%3,%4};" ::"l"(p), "r"(v.x), "r"(v.y), "r"(v.z), "r"(v.w) : "memory"); }
__device__ __forceinline__ uint4 ldg_nc4(const void* p) { uint4 v; asm volatile("ld.global.nc.L1::no_allocate.v4.u32 {%0,%1,%2,%3}, [%4];" : "=r"(v.x), "=r"(v.y), "=r"(v.z), "=r"(v.w) : "l"(p)); return v; }
__device__ __forceinline__ uint32_t ldg_nc(const void* p) { uint32_t v; asm volatile("ld.global.nc.u32 %0, [%1];" : "=r"(v) : "l"(p)); return v; }
__device__ __forceinline__ uint32_t ld_acquire(const uint32_t* p) { uint32_t v; asm volatile("ld.acquire.gpu.global.u32 %0, [%1];" : "=r"(v) : "l"(p) : "memory"); return v; }
__device__ __forceinline__ uint4 lds4(uint32_t a) { uint4 v; asm volatile("ld.shared.v4.u32 {%0,%1,%2,%3}, [%4];" : "=r"(v.x), "=r"(v.y), "=r"(v.z), "=r"(v.w) : "r"(a) : "memory"); return v; }
__device__ __forceinline__ float2 lds2f(uint32_t a) { float2 v; asm volatile("ld.shared.v2.f32 {%0,%1}, [%2];" : "=f"(v.x), "=f"(v.y) : "r"(a) : "memory"); return v; }
__device__ __forceinline__ uint32_t lds1(uint32_t a) { uint32_t v; asm volatile("ld.shared.u32 %0, [%1];" : "=r"(v) : "r"(a) : "memory"); return v; }
__device__ __forceinline__ void sts4(uint32_t a, uint4 v) { asm volatile("st.shared.v4.u32 [%0], {%1,%2,%3,%4};" ::"r"(a), "r"(v.x), "r"(v.y), "r"(v.z), "r"(v.w) : "memory"); }
__device__ __forceinline__ void sts2(uint32_t a, uint32_t x, uint32_t y) { asm volatile("st.shared.v2.u32 [%0], {%1,%2};" ::"r"(a), "r"(x), "r"(y) : "memory"); }
__device__ __forceinline__ void sts1(uint32_t a, uint32_t v) { asm volatile("st.shared.u32 [%0], %1;" ::"r"(a), "r"(v) : "memory"); }
__device__ __forceinline__ void stsm4(uint32_t a, uint32_t r0, uint32_t r1, uint32_t r2, uint32_t r3) {
    asm volatile("stmatrix.sync.aligned.m8n8.x4.shared.b16 [%0], {%1,%2,%3,%4};" ::"r"(a), "r"(r0), "r"(r1), "r"(r2), "r"(r3));
}
__device__ __forceinline__ uint32_t pack2(float lo, float hi) { uint32_t r; asm("cvt.rn.bf16x2.f32 %0, %1, %2;" : "=r"(r) : "f"(hi), "f"(lo)); return r; }
__device__ __forceinline__ uint32_t pack2_relu(float lo, float hi) { uint32_t r; asm("cvt.rn.relu.bf16x2.f32 %0, %1, %2;" : "=r"(r) : "f"(hi), "f"(lo)); return r; }
__device__ __forceinline__ uint32_t hfma2(uint32_t a, uint32_t b, uint32_t c) { uint32_t r; asm("fma.rn.bf16x2 %0, %1, %2, %3;" : "=r"(r) : "r"(a), "r"(b), "r"(c)); return r; }
__device__ __forceinline__ uint32_t hmul2(uint32_t a, uint32_t b) { uint32_t r; asm("mul.rn.bf16x2 %0, %1, %2;" : "=r"(r) : "r"(a), "r"(b)); return r; }
__device__ __forceinline__ float bf_lo(uint32_t v) { return __uint_as_float(v << 16); }
__device__ __forceinline__ float bf_hi(uint32_t v) { return __uint_as_float(v & 0xFFFF0000u); }
__device__ __forceinline__ float bf_round(float v) { return bf_lo(pack2(v, 0.f)); }
__device__ __forceinline__ float ex2(float x) { float r; asm("ex2.approx.ftz.f32 %0, %1;" : "=f"(r) : "f"(x)); return r; }
__device__ __forceinline__ void mma16816(float* d, uint32_t a0, uint32_t a1, uint32_t a2, uint32_t a3, uint32_t b0, uint32_t b1) {
    asm("mma.sync.aligned.m16n8k16.row.col.f32.bf16.bf16.f32 {%0,%1,%2,%3}, {%4,%5,%6,%7}, {%8,%9}, {%0,%1,%2,%3};"
        : "+f"(d[0]), "+f"(d[1]), "+f"(d[2]), "+f"(d[3]) : "r"(a0), "r"(a1), "r"(a2), "r"(a3), "r"(b0), "r"(b1));
}
__device__ __forceinline__ void mma16816_first(float* d, uint32_t a0, uint32_t a1, uint32_t a2, uint32_t a3, uint32_t b0, uint32_t b1) {
    asm volatile("mma.sync.aligned.m16n8k16.row.col.f32.bf16.bf16.f32 {%0,%1,%2,%3}, {%4,%5,%6,%7}, {%8,%9}, {%10,%10,%10,%10};"
        : "=f"(d[0]), "=f"(d[1]), "=f"(d[2]), "=f"(d[3]) : "r"(a0), "r"(a1), "r"(a2), "r"(a3), "r"(b0), "r"(b1), "f"(0.f));
}
__device__ __forceinline__ void mma16816_v(float* d, uint32_t a0, uint32_t a1, uint32_t a2, uint32_t a3, uint32_t b0, uint32_t b1) {
    asm volatile("mma.sync.aligned.m16n8k16.row.col.f32.bf16.bf16.f32 {%0,%1,%2,%3}, {%4,%5,%6,%7}, {%8,%9}, {%0,%1,%2,%3};"
        : "+f"(d[0]), "+f"(d[1]), "+f"(d[2]), "+f"(d[3]) : "r"(a0), "r"(a1), "r"(a2), "r"(a3), "r"(b0), "r"(b1));
}
__device__ __forceinline__ void mma1688(float* d, uint32_t a0, uint32_t a1, uint32_t b0) {
    asm("mma.sync.aligned.m16n8k8.row.col.f32.bf16.bf16.f32 {%0,%1,%2,%3}, {%4,%5}, {%6}, {%0,%1,%2,%3};"
        : "+f"(d[0]), "+f"(d[1]), "+f"(d[2]), "+f"(d[3]) : "r"(a0), "r"(a1), "r"(b0));
}
__device__ __forceinline__ void ldsm4(uint32_t a, uint32_t* r) {
    asm volatile("ldmatrix.sync.aligned.m8n8.x4.shared.b16 {%0,%1,%2,%3}, [%4];" : "=r"(r[0]), "=r"(r[1]), "=r"(r[2]), "=r"(r[3]) : "r"(a));
}
__device__ __forceinline__ void ldsm4t(uint32_t a, uint32_t* r) {
    asm volatile("ldmatrix.sync.aligned.m8n8.x4.trans.shared.b16 {%0,%1,%2,%3}, [%4];" : "=r"(r[0]), "=r"(r[1]), "=r"(r[2]), "=r"(r[3]) : "r"(a));
}
__device__ __forceinline__ uint32_t nz(uint32_t v) { uint32_t r; asm("max.u32 %0, %1, 1;" : "=r"(r) : "r"(v)); return r; }
__device__ __forceinline__ float rcp(float x) { float r; asm("rcp.approx.ftz.f32 %0, %1;" : "=f"(r) : "f"(x)); return r; }
__device__ __forceinline__ uint2 ld_relaxed2(const void* p) { uint2 v; asm volatile("ld.relaxed.gpu.global.v2.u32 {%0,%1}, [%2];" : "=r"(v.x), "=r"(v.y) : "l"(p) : "memory"); return v; }
__device__ __forceinline__ void st_relaxed2(void* p, uint32_t x, uint32_t y) { asm volatile("st.relaxed.gpu.global.v2.u32 [%0], {%1,%2};" ::"l"(p), "r"(max(x, 1u)), "r"(max(y, 1u)) : "memory"); }
__host__ __device__ constexpr uint64_t dconst(uint32_t lbo, uint32_t sbo, uint32_t swz) {
    return ((uint64_t)(lbo >> 4) << 16) | ((uint64_t)(sbo >> 4) << 32) | ((uint64_t)swz << 62);
}
__device__ __forceinline__ uint32_t mkdesc(uint32_t addr, uint64_t c) { return (uint32_t)c | ((addr & 0x3FFFF) >> 4); }
#define WG_FENCE() asm volatile("wgmma.fence.sync.aligned;" ::: "memory")
#define WG_COMMIT() asm volatile("wgmma.commit_group.sync.aligned;" ::: "memory")
#define WG_WAIT(n) asm volatile("wgmma.wait_group.sync.aligned %0;" ::"n"(n) : "memory")
template <int N> __device__ __forceinline__ void reg_fence(float* d) {
#pragma unroll
    for (int i = 0; i < N; i++) asm volatile("" : "+f"(d[i])::"memory");
}
template <int N> __device__ __forceinline__ void reg_def(float* d) {
#pragma unroll
    for (int i = 0; i < N; i++) asm volatile("" : "=f"(d[i]));
}
template <int N> __device__ __forceinline__ void reg_def(uint32_t* d) {
#pragma unroll
    for (int i = 0; i < N; i++) asm volatile("" : "=r"(d[i]));
}
__device__ __forceinline__ bool is_unset(uint4 v) { return min(min(v.x, v.y), min(v.z, v.w)) == 0u; }
__device__ __forceinline__ uint4 nz4(uint32_t a, uint32_t b, uint32_t c, uint32_t d) { return make_uint4(max(a, 1u), max(b, 1u), max(c, 1u), max(d, 1u)); }
__device__ __forceinline__ void wait_flags(const uint32_t* p, uint32_t target, uint32_t mask) {
    int n = 0;
    while (~__ballot_sync(~0u, (int)(ld_relaxed(p) - target) >= 0) & mask) { if (++n > SPIN_LIMIT) __trap(); }
    asm volatile("fence.acquire.gpu;" ::: "memory");
}
__device__ __forceinline__ float silu_bf(uint32_t cbits) {
    const float c = __uint_as_float(cbits << 16);
    return bf_round(__fdividef(c, 1.f + fminf(ex2(-1.4426950408889634f * c), 1e30f)));
}
__device__ __forceinline__ void gemv_part(uint32_t wmbuf, int wp, int lane) {
    const uint32_t wa = wmbuf + wp * 512 + (8 * (lane >> 4) + (lane & 7)) * 32 + ((lane >> 3) & 1) * 16;
    float d[4] = {};
#pragma unroll
    for (int i = 0; i < 4; i++) {
        uint32_t A[4];
        const float2 v = lds2f(wmbuf + 28672 + (wp + 8 * i) * 32 + (lane & 3) * 8);
        ldsm4t(wa + (i < 3 || wp < 4 ? i : 0) * 4096, A);
        mma16816(d, A[0], A[1], A[2], A[3], __float_as_uint(v.x), __float_as_uint(v.y));
    }
    if ((lane & 3) == 0) {
        sts1(wmbuf + 29696 + (wp * 16 + (lane >> 2)) * 4, __float_as_uint(d[0]));
        sts1(wmbuf + 29696 + (wp * 16 + 8 + (lane >> 2)) * 4, __float_as_uint(d[2]));
    }
}
__device__ __forceinline__ uint32_t mod_word(float v, int col, uint32_t target) {
    v = bf_round(v);
    if ((col >= DM && col < 2 * DM) || (col >= 4 * DM && col < 5 * DM)) v += 1.f;
    return (pack2(v, 0.f) << 16) | (target & 0xFFFFu);
}
__device__ __forceinline__ const uint4* mod_src(int i, int r, int j, bool p2) {
    i = min(i, p2 ? 251 : 223);
    return (const uint4*)g_mod + (r & 7) * (6 * DM / 4) + (i < 224 ? (p2 ? 336 : 0) + i : (i < 238 ? 14 * j + i : 14 * j + i + 322));
}
__device__ __forceinline__ void mod_store(uint32_t sb, uint4 v, const uint4* src, int i) {
    const uint32_t tag = lds1(sb + M_EPOCH) + 1;
    while (__any_sync(~0u, (((v.x ^ tag) | (v.y ^ tag) | (v.z ^ tag) | (v.w ^ tag)) & 0xFFFFu) != 0u)) v = ld_relaxed4(src);
    if (i < 224) {
        const int isc = i >= 112, c4 = i - 112 * isc;
        const uint32_t a = sb + M_ST + (c4 >> 2) * 64 + (c4 & 1) * 32 + (c4 & 2) * 4 + (isc ? 0 : 4);
        sts1(a, __byte_perm(v.x, v.y, 0x7632));
        sts1(a + 16, __byte_perm(v.z, v.w, 0x7632));
    } else if (i < 252) {
        sts4(sb + M_G + (i - 224) * 16, make_uint4(v.x & 0xFFFF0000u, v.y & 0xFFFF0000u, v.z & 0xFFFF0000u, v.w & 0xFFFF0000u));
    }
}
__device__ __forceinline__ int pass_f(int fs, int ps) { return 224 * fs + ((fs & 1) ? (ps == 0 ? 96 : ps == 1 ? 32 : 0) : (ps == 0 ? 0 : ps == 1 ? 128 : 192)); }
__device__ __forceinline__ constexpr uint32_t slot_off(int l) { return l * 16384; }
__device__ __forceinline__ constexpr int g1_slot(int s) { return s % 7; }
__device__ __noinline__ void x1_fix(const uint32_t* g, uint32_t sa, int s) {
#pragma unroll 1
    for (int k = 4 * s; k < 4 * s + 4;) {
        const uint4 v = ld_relaxed4((const uint4*)(g + k * 256));
        sts4(sa + k * 1024, v);
        k += 2 * __all_sync(~0u, min(min(v.x, v.y), min(v.z, v.w)) != 0u);
    }
    __syncwarp();
}
__device__ __forceinline__ void ln_coeffs(float mean, float msq, uint32_t& r2, uint32_t& n2) {
    const float rs = bf_round(rsqrtf(fmaxf(msq - mean * mean, 0.f) + 1e-5f));
    r2 = pack2(rs, rs);
    n2 = pack2(-mean * rs, -mean * rs);
}

#define LOADW bulk_e(dst, g_wd + (size_t)((f >> 5) * 4 + nq) * 1792, 7168, bar);
template <int sec> __device__ __forceinline__ void ring_loader(const Params& p, uint32_t sb_, int r_, int j_, int lane) {
    const uint32_t sb = opaque(sb_);
    const int r = opaque(r_), j = opaque(j_), nq = j >> 1, fs = 4 * (j & 1) + nq;
    const int fa = pass_f(fs, 0), fb = pass_f(fs, 1), fc = pass_f(fs, 2);
    const uint32_t* h2src = (const uint32_t*)__shfl_sync(~0u, (unsigned long long)(p.actb + (size_t)r * RB_WORDS + RB_H2), 0);
    const CUtensorMap* gmap = (const CUtensorMap*)__shfl_sync(~0u, (unsigned long long)(&p.ga + sec), 0);
#define BAR(i) (sb + M_BAR + 8 * (i))
#define kh (j & 1)
            int sl = 0;
#pragma unroll 1
            for (int s = 0; s < 28; s++) {
                if (s == 7) { wait_flags(g_flag + (8 * r + j) * 128 + 96 + lane, lds1(sb + M_EPOCH) + 1, 0xFFFFu); fence_async_global(); }
                const int ps = s < 14 ? 0 : s < 21 ? 1 : 2;
                const uint32_t half = ps < 2 ? 8192 : 4096;
                const int sp = sl;
                if (s >= PACE && s < PACE_END) mbar_wait(BAR(B_FULL + s - PACE), 0);
                mbar_wait(BAR(B_EMPTY + sp), (s >= 7 && s < 14) || s >= 21);
                expect_e(BAR(B_FULL + sp), half);
                tma3_e(sb + slot_off(sp) + sec * half, gmap + 2 * ps, 0, ps ? 64 * sl : 32 * s, ps == 0 ? fa >> 6 : ps == 1 ? fb >> 6 : fc >> 5, BAR(B_FULL + sp));
                sl = sl == 6 ? 0 : sl + 1;
            }
            if (!sec) PROFH(3);
#pragma unroll 1
            for (int e = 0; e < 4; e++) {
                const uint32_t dst = sb + slot_off(e) + sec * 8192, bar = BAR(B_FULL + e);
                const int f = (e < 2 ? fa + 64 * e : e == 2 ? fb : fc) + 32 * sec;
                mbar_wait(BAR(B_EMPTY + e), 0);
                expect_e(bar, e == 3 && sec ? 0 : 7168);
                if (!(e == 3 && sec)) { LOADW }
            }
            sl = 4;
            int e = 4;
#pragma unroll 1
            for (int grp = 0; grp < 9; grp++) {
                const int ps = grp >= 6 ? 2 : grp >= 3 ? 1 : 0;
                int sidx = grp - 3 * ps;
                if (sec && sidx == 0) { mbar_wait(BAR(B_HRDY + ps), 0); fence_async_global(); }
                sidx += sidx >= nq;
                int f = pass_f(4 * kh + sidx, ps);
#pragma unroll 1
                for (int k = 4 >> ps; k > 0; k--, e++, f += 32) {
                    const uint32_t dst = sb + slot_off(sl), bar = BAR(B_FULL + sl);
                    mbar_wait(BAR(B_EMPTY + sl), e >= 12 && e < 24);
                    if (e < WIN_END && e >= WIN) mbar_wait(BAR(B_FULL + (sl >= WIN ? sl - WIN : sl + 12 - WIN)), e - WIN >= 12);
                    expect_e(bar, sec ? 8192 : 7168);
                    if (!sec) { LOADW }
                    else bulk_e(dst + 8192, h2src + f * 64, 8192, bar);
                    sl = sl == 11 ? 0 : sl + 1;
                }
            }
            if (!sec) PROFH(4);
}

#define PROF_PARAMS
#define PROF_ARGS
__device__ __noinline__ void helper_late(const Params& p, int r_, int j_, int warp_ PROF_PARAMS) {
    extern __shared__ __align__(1024) unsigned char smem[];
    const uint32_t sb = (uint32_t)__cvta_generic_to_shared(smem);
    const int r = opaque(r_), j = opaque(j_), warp = opaque(warp_), nq = j >> 1, b = 8 * r + j;
    uint32_t* const act = (uint32_t*)__shfl_sync(~0u, (unsigned long long)(p.actb + (size_t)r * RB_WORDS), 0);
    {
        const int lane = fresh_tid() & 31;
        const uint32_t target = lds1(sb + M_EPOCH) + 1;
        if (warp == 8) { expect_e(BAR(B_XCH), 14336); expect_e(BAR(B_XCH + 1), 14336); }
            if (warp == 9) {
#pragma unroll 1
                for (int kv = 0; kv < 2; kv++) {
                    mbar_wait(BAR(B_PUB + kv), 0);
                    wait_flags(g_flag + b * 128 + lane, target, (r >= 2 ? 6u : r == 1 ? 2u : 0u) << (8 * kv));
                    fence_async_global();
                    const uint32_t dst = sb + OFF_Y + (kv ? Y_VR : Y_K);
                    expect_e(BAR(B_KRFULL + kv), r >= 2 ? 28672 : r == 1 ? 14336 : 0);
                    if (r >= 2) bulk_e(dst, act - 2 * RB_WORDS + RB_KV + j * 7168 + kv * 3584, 14336, BAR(B_KRFULL + kv));
                    if (r >= 1) bulk_e(dst + 14336, act - RB_WORDS + RB_KV + j * 7168 + kv * 3584, 14336, BAR(B_KRFULL + kv));
                }
            } else if (warp == 8) {
                uint4 v[8];
                mbar_wait(BAR(B_PUB + 2), 0);
#pragma unroll
                for (int k = 0; k < 8; k++) v[k] = ld_relaxed4(mod_src(lane + 32 * k, r, j, true));
#pragma unroll
                for (int k = 0; k < 8; k++) mod_store(sb, v[k], mod_src(lane + 32 * k, r, j, true), lane + 32 * k);
                warp_arrive(BAR(B_MOD1));
            } else if (warp == 11) {
                if (kh == 1 && r < 14) {
                    const uint32_t wmbuf = sb + OFF_X;
                    const int mcol = 2 * DM + 32 * (4 * r + nq);
                    mbar_wait(BAR(B_VRFULL), 0);
                    mbar_wait(BAR(B_XFREE), 1);
#pragma unroll 1
                    for (int k = 0; k < 4; k++) tma3_e(wmbuf + k * 7168, &p.wm, mcol + (k >> 1) * 16, (k & 1) * 224, 0, BAR(B_WMFULL));
#pragma unroll 1
                    for (int wd = lane; wd < 224; wd += 32) {
                        const uint32_t cb = __ldg((const uint32_t*)p.c + wd);
                        sts1(wmbuf + 28672 + (wd >> 3) * 32 + (wd & 3) * 8 + (wd & 4), pack2(silu_bf(cb & 0xFFFFu), silu_bf(cb >> 16)));
                    }
                    __syncwarp();
                    mbar_wait(BAR(B_WMFULL), 0);
                    const uint32_t wa = wmbuf + (8 * (lane >> 4) + (lane & 7)) * 32 + ((lane >> 3) & 1) * 16;
                    float d[2][4] = {};
#pragma unroll 4
                    for (int ks = 0; ks < 28; ks++) {
                        uint32_t A[8];
                        ldsm4t(wa + ks * 512, A); ldsm4t(wa + 14336 + ks * 512, A + 4);
                        const float2 v = lds2f(wmbuf + 28672 + ks * 32 + (lane & 3) * 8);
                        mma16816(d[0], A[0], A[1], A[2], A[3], __float_as_uint(v.x), __float_as_uint(v.y));
                        mma16816(d[1], A[4], A[5], A[6], A[7], __float_as_uint(v.x), __float_as_uint(v.y));
                    }
                    const int q = lane & 3, col = mcol + 8 * q + (lane >> 2);
                    const uint32_t word = mod_word(q == 0 ? d[0][0] : q == 1 ? d[0][2] : q == 2 ? d[1][0] : d[1][2], col, target);
#pragma unroll
                    for (int i = 0; i < 8; i++) st_relaxed(g_mod + i * 6 * DM + col, word);
                }
                warp_arrive(BAR(B_WMFREE));
                mbar_wait(BAR(B_VRFULL), 0);
                l2_prefetch_e((const char*)p.wg + (size_t)b * 12544, 12544);
                l2_prefetch_e((const char*)p.wu + (size_t)b * 12544, 12544);
#pragma unroll 1
                for (int k = 0; k < (r < 12 ? 2 : 1); k++) {
                    const int u = 28 * kh + r + 16 * k;
                    expect_e(BAR(B_XFULL + k), 7168);
                    tma3_e(sb + OFF_Y + 102400, &p.dn, 0, 32 * u, 7 * j, BAR(B_XFULL + k));
                    tma3_e(sb + OFF_Y + 102400 + 3584, &p.dn, 0, 32 * u, 7 * (j ^ 1), BAR(B_XFULL + k));
                    mbar_wait(BAR(B_XFULL + k), 1);
                    asm volatile("{\n.reg .pred p;\nelect.sync _|p, 0xffffffff;\n@p cp.async.bulk.global.shared::cta.bulk_group [%0], [%1], 7168;\n"
                                 "cp.async.bulk.commit_group;\ncp.async.bulk.wait_group 0;\n}" ::"l"(g_wd + (size_t)(u * 4 + nq) * 1792), "r"(sb + OFF_Y + 102400) : "memory");
                    __syncwarp();
                }
                warp_arrive(BAR(B_FULLK));
                fence_gpu();
                if (lane < 16) st_relaxed(g_flag + (8 * lane + j) * 128 + 96 + r, target);
            }
        if (warp == 8 || warp == 11) {
            const int sec = warp == 11;
            if (sec) ring_loader<1>(p, sb, r, j, lane); else ring_loader<0>(p, sb, r, j, lane);
            mbar_wait(BAR(B_DONE), 0);
        } else if (warp == 9) {
#pragma unroll
            for (int ev = 0; ev < 4; ev++) { expect_e(BAR(B_GFULL + ev), ev < 2 ? HALF / 2 : 16384 + 4096); expect_e(BAR(B_XFULL + 2 + ev), ev < 2 ? HALF / 2 : HALF - 16384); }
            mbar_wait(BAR(B_WMFREE), 0);
            mbar_wait(BAR(B_PUB + 2), 0);
            const uint32_t* fp = g_flag + b * 128 + 32 + lane;
            const int par = (target - 1) & 1;
#pragma unroll 1
            for (int n = 0, ev = 0; ev < 4; n++) {
                if (ev == 1) { mbar_wait(BAR(B_FULLK), 1); mbar_wait(BAR(B_PUB + 3), 0); }
                uint32_t ok = __ballot_sync(~0u, (int)(ld_relaxed(fp) - target) >= 0) >> (8 * ev);
                while ((ok & 0xFFu) == 0xFFu) {
                    asm volatile("fence.acquire.gpu;" ::: "memory");
                    fence_async_global();
                    const int tile = (ev & 1) + (ev >> 1) * par * 2;
                    const uint32_t dst = sb + (ev == 0 ? OFF_X : OFF_Y + (ev & 1) * HALF), first = ev < 2 ? HALF / 2 : 16384;
                    const char* src = (const char*)(act + RB_O + ((ev >> 1) * 2 + tile) * 14336);
                    if (ev >= 2) bulk_e(sb + OFF_X + X_STAT + (ev & 1) * 49152, act + RB_ST + tile * 1024, 4096, BAR(B_GFULL + ev));
                    bulk_e(dst, src, first, BAR(B_GFULL + ev));
                    bulk_e(dst + first, src + first, HALF - first, BAR(B_XFULL + 2 + ev));
                    if (ev) PROFH(4 + ev);
                    ev++; ok >>= 8;
                }
                if (n > SPIN_LIMIT) __trap();
            }
            mbar_wait(BAR(B_XFULL + 5), 1);
#pragma unroll 1
            for (int hf = 0; hf < 2; hf++) {
                const int tile = (par ^ 1) * 2 + hf;
                uint4* xz = (uint4*)(act + RB_X1 + tile * 14336 + j * 1792) + lane;
#pragma unroll
                for (int i = 0; i < 14; i++) xz[i * 32] = make_uint4(0, 0, 0, 0);
                ((uint4*)(act + RB_ST + (tile * 8 + j) * 128))[lane] = make_uint4(0, 0, 0, 0);
            }
#pragma unroll 1
            for (int ps = 0; ps < 3; ps++) {
                mbar_wait(BAR(B_PUB + 6 + ps), 0);
                wait_flags(g_flag + b * 128 + 64 + lane, target, (0x55u << kh) << (8 * ps));
                warp_arrive(BAR(B_HRDY + ps));
                PROFH(9 + ps);
            }
        } else {
#pragma unroll 1
            for (int k = 0; k < 9; k++) {
                uint32_t* fp = k < 2 ? g_flag + (b + 8 * lane) * 128 + k * 8 + lane : g_flag + (8 * r + lane) * 128 + 16 + k * 8 + j;
                mbar_wait(BAR(B_PUB + k), 0);
                if (k != 4 && k != 5) fence_gpu();
                if (k < 2 ? (lane == 1 || lane == 2) : lane < 8) st_relaxed(fp, target);
                if (k >= 3 && k <= 5) PROFH(k - 3);
            }
        }
    }
}

__global__ void __cluster_dims__(2, 1, 1) __launch_bounds__(384, 1) fused_block_kernel(const __grid_constant__ Params p) {
    extern __shared__ __align__(1024) unsigned char smem[];
    const uint32_t sb = (uint32_t)__cvta_generic_to_shared(smem);
    const int tid = threadIdx.x, lane = tid & 31, warp = __shfl_sync(~0u, tid >> 5, 0);
    const int m = blockIdx.x >> 1;
    int r, nq;
    if (m < 4) { r = 15; nq = m; }
    else if (m < 36) { r = (m - 4) & 7; nq = (m - 4) >> 3; }
    else { nq = (m - 36) / 7; r = m - 28 - 7 * nq; }
    const int j = opaque(2 * nq + (blockIdx.x & 1)), b = 8 * r + j, fs = 4 * kh + nq;
#define act (p.actb + (size_t)r * RB_WORDS)
    constexpr uint32_t sc = 0;
    if (lane == 0 && warp < 9 && warp != 6 && warp != 7) {
        const int i0 = warp == 8 ? 0 : 8 + 8 * warp, cnt = warp == 0 || warp == 8 ? 1 : warp < 3 ? 2 : 8;
#pragma unroll
        for (int k = 0; k < 8; k++) if (i0 + k != B_WMFULL) mbar_init(BAR(i0 + k), cnt);
        asm volatile("fence.mbarrier_init.release.cluster;" ::: "memory");
        fence_async_smem();
    }

    if (warp >= 8) {
        const int lane = fresh_tid() & 31;
        const bool early = kh == 0, gemv = r < 14;
        const int mcol = early ? 16 * (4 * r + nq) : 2 * DM + 32 * (4 * r + nq);
        const uint32_t wmbuf = sb + OFF_Y + HALF;
        asm volatile("setmaxnreg.dec.sync.aligned.u32 56;");
        if (warp == 9) {
#pragma unroll
            for (int i = 56; i < 64; i++) init_e(BAR(i), 1);
            fence_async_smem();
        }
        if (warp == 8) { init_e(BAR(B_WMFULL), 1); fence_async_smem(); }
        bar_arrive(0, 384);
        asm volatile("barrier.cluster.arrive.relaxed.aligned;" ::: "memory");
        if (warp == 8) {
            if (!sc) {
                expect_e(BAR(B_WMFULL), gemv ? 28672 >> early : 0);
                if (early && gemv) { tma3_e(wmbuf, &p.wm, mcol, 0, 0, BAR(B_WMFULL)); tma3_e(wmbuf + 7168, &p.wm, mcol, 224, 0, BAR(B_WMFULL)); }
#pragma unroll 1
                for (int kb = 0; kb < 7; kb++) {
                    expect_e(BAR(B_XFULL + kb), 16384);
                    tma3_e(sb + OFF_X + kb * 16384, &p.xm, 64 * kb, 128 * r, 0, BAR(B_XFULL + kb));
                }
            }
#pragma unroll 1
            for (int mt = 0; mt < 4; mt++) {
                if (mt == 1) bar_sync(9, 384);
                if (mt) mbar_wait(BAR(mt == 1 ? B_MOD1 : mt == 2 ? B_XFREE : B_VRFULL), 0);
                const uint32_t bar = BAR(mt == 3 ? B_WOFULL : B_FULLK + mt), dst = sb + (mt < 2 ? OFF_Y : OFF_X) + (mt & 1) * HALF;
                const int c0 = (mt < 2 ? DM + DM * mt : 0) + 56 * j - 8 * kh;
                if (!sc) {
                    expect_e(bar, HALF);
                    tma3_e(dst, mt == 3 ? &p.wo : &p.qkv, c0, 0, 0, bar);
                    tma3_e(dst + HALF / 2, mt == 3 ? &p.wo : &p.qkv, c0, 224, 0, bar);
                }
            }
        } else {
            if (warp == 10 && !sc) l2_prefetch_e((const char*)p.wqkv + (size_t)b * 9408, 9408);
            bar_sync(9, 384);
            if (sc) return;
            if (warp == 11 && early) {
                const uint32_t target = lds1(sb + M_EPOCH) + 1;
                mbar_wait(BAR(B_GEMV), 0);
                float sum = 0.f;
#pragma unroll
                for (int i = 0; i < 8; i++) sum += *(const float*)(smem + OFF_Y + HALF + 29696 + (i * 16 + (lane & 15)) * 4);
                uint32_t* mg = g_mod + mcol + (lane & 15) + (lane >> 4) * 4 * 6 * DM;
                const uint32_t word = mod_word(sum, mcol, target);
                if (gemv) { st_relaxed(mg, word); st_relaxed(mg + 6 * DM, word); st_relaxed(mg + 12 * DM, word); st_relaxed(mg + 18 * DM, word); }
            }
        }
    }
    if (LIKELY(warp < 8)) {
        const int w = warp >> 2, wi = warp & 3;
#define COORDS const int t = fresh_tid() & 127, lane = t & 31, q = lane & 3, lr = lane >> 2, ra = 64 * w + 16 * wi + lr; \
        const uint32_t lx = (lane >> 4) ^ (lane & 7), mrow = (64 * w + 16 * wi + ((lane >> 3) & 1) * 8 + (lane & 7)) * 128; \
        (void)q; (void)lr; (void)ra; (void)lx; (void)mrow;
        const int sid = 2 * (j & 3) + w;
#define RUN(k) (!sc || sid == (k))
#define WAIT(i, par) mbar_wait_c(BAR(i), (par) | sc)
        constexpr uint64_t DB128 = dconst(4096, 1024, 1);
        {
            const int wd = fresh_tid();
            const uint32_t cb = wd < 224 ? __ldg((const uint32_t*)p.c + wd) : 0u;
            if (wd == 255 && !sc) sts1(sb + M_EPOCH, atomicAdd(&g_ticket, 1u) / NCTA);
            sts1(sb + OFF_Y + HALF + 28672 + (wd >> 3) * 32 + (wd & 3) * 8 + (wd & 4), pack2(silu_bf(cb & 0xFFFFu), silu_bf(cb >> 16)));
        }
        bar_arrive(9, 384);
        bar_sync(0, 384);
        asm volatile("barrier.cluster.arrive.relaxed.aligned;" ::: "memory");
        asm volatile("setmaxnreg.inc.sync.aligned.u32 224;");
        PROFC(0);
        uint32_t xr[16];
        {
            COORDS
            uint32_t h[112];
            uint32_t ra2, na2, rb2, nb2;
            const int mi = min(128 * w + t, 223);
            const uint4* msrc = mod_src(mi, r, j, false);
            uint4 mv;
            {
                float ds[4] = {}, da[2][4] = {}, db[2][4] = {};
                const uint32_t ONE2 = 0x3F803F80u;
#pragma unroll
                for (int kb = 0; kb < 7; kb++) {
                    if (kb == GEMV_AT && kh == 0) { WAIT(B_WMFULL, 0); gemv_part(sb + OFF_Y + HALF, warp, lane); warp_arrive(BAR(B_GEMV)); }
                    WAIT(B_XFULL + kb, 0);
#pragma unroll
                    for (int k4 = 0; k4 < 4; k4++) ldsm4(sb + OFF_X + mrow + kb * 16384 + (((2 * k4) ^ lx) << 4), h + 16 * kb + 4 * k4);
#pragma unroll
                    for (int k4 = 0; k4 < 4; k4++) {
                        const uint32_t* f = h + 16 * kb + 4 * k4;
                        mma16816(ds, f[0], f[1], f[2], f[3], ONE2, ONE2);
                        mma1688(da[0], f[0], f[1], f[0]); mma1688(db[0], f[0], f[1], f[1]);
                        mma1688(da[1], f[2], f[3], f[2]); mma1688(db[1], f[2], f[3], f[3]);
                    }
                }
#pragma unroll
                for (int i = 0; i < 4; i++) {
                    const int ch = 7 * j + 2 * i + (lane >> 4);
                    ldsm4(sb + OFF_X + mrow + (ch >> 3) * 16384 + (((ch ^ lane) & 7) << 4), xr + 4 * i);
                }
                mv = ld_relaxed4(msrc);
                warp_arrive(BAR(B_XFREE));
                float qa = (lr & 1) ? da[0][1] + da[1][1] : da[0][0] + da[1][0];
                float qb = (lr & 1) ? db[0][3] + db[1][3] : db[0][2] + db[1][2];
                const int src = (lane & ~3) | (lr >> 1);
                qa = __shfl_sync(~0u, qa, src);
                qb = __shfl_sync(~0u, qb, src);
                ln_coeffs(ds[0] * (1.f / DM), qa * (1.f / DM), ra2, na2);
                ln_coeffs(ds[2] * (1.f / DM), qb * (1.f / DM), rb2, nb2);
#pragma unroll
                for (int i = 0; i < 4 * NPRE; i += 2) { h[i] = hfma2(h[i], ra2, na2); h[i + 1] = hfma2(h[i + 1], rb2, nb2); }
            }
            PROFC(1);
            {
                float ak[28], av[28], aq[28];
                uint32_t kp[14], vp[14];
                const uint64_t bq0 = (DB128 & ~0xFFFFFFFFull) | (mkdesc(sb + OFF_X, DB128) + kh), bk0 = bq0 + (OFF_Y >> 4), bv0 = bk0 + (HALF >> 4);
                uint32_t* kvg = act + RB_KV + j * 7168 + (8 * w + 2 * wi) * 224 + lane;
                mod_store(sb, mv, msrc, mi);
                bar_sync(3, 256);
                if (warp == 0) warp_arrive(BAR(B_MOD1));
                WAIT(B_FULLK, 0);
                PROFC(2);
                reg_def<28>(ak);
#pragma unroll
                for (int g4 = 0; g4 < 4; g4++) {
#pragma unroll
                    for (int ks = 7 * g4; ks < 7 * g4 + 7; ks++) {
                        const uint4 st = *(const uint4*)(smem + M_ST + ks * 64 + q * 16);
                        if (ks >= NPRE) {
                            h[4 * ks] = hfma2(h[4 * ks], ra2, na2); h[4 * ks + 1] = hfma2(h[4 * ks + 1], rb2, nb2);
                            h[4 * ks + 2] = hfma2(h[4 * ks + 2], ra2, na2); h[4 * ks + 3] = hfma2(h[4 * ks + 3], rb2, nb2);
                        }
                        h[4 * ks] = hfma2(h[4 * ks], st.x, st.y); h[4 * ks + 1] = hfma2(h[4 * ks + 1], st.x, st.y);
                        h[4 * ks + 2] = hfma2(h[4 * ks + 2], st.z, st.w); h[4 * ks + 3] = hfma2(h[4 * ks + 3], st.z, st.w);
                    }
                    WG_FENCE();
#pragma unroll
                    for (int ks = 7 * g4; ks < 7 * g4 + 7; ks++) wgmma_rl_56(ak, h[4 * ks], h[4 * ks + 1], h[4 * ks + 2], h[4 * ks + 3], bk0 + ks * 128, ks != 0);
                }
                WG_COMMIT();
                PROFC(3);
                WAIT(B_FULLV, 0);
                reg_def<28>(av);
                WG_FENCE();
#pragma unroll
                for (int ks = 0; ks < 8; ks++) wgmma_rl_56(av, h[4 * ks], h[4 * ks + 1], h[4 * ks + 2], h[4 * ks + 3], bv0 + ks * 128, ks != 0);
                WG_COMMIT();
                WG_WAIT(1);
                reg_fence<28>(ak);
#pragma unroll
                for (int g = 0; g < 7; g++) {
                    kp[2 * g] = pack2(ak[4 * g], ak[4 * g + 1]); kp[2 * g + 1] = pack2(ak[4 * g + 2], ak[4 * g + 3]);
                    kvg[g * 32] = kp[2 * g]; kvg[224 + g * 32] = kp[2 * g + 1];
                }
                warp_arrive(BAR(B_PUB));
                PROFC(4);
                WG_FENCE();
#pragma unroll
                for (int ks = 8; ks < 28; ks++) wgmma_rl_56(av, h[4 * ks], h[4 * ks + 1], h[4 * ks + 2], h[4 * ks + 3], bv0 + ks * 128, 1);
                WG_COMMIT();
                WAIT(B_FULLQ, 0);
                reg_def<28>(aq);
                WG_FENCE();
#pragma unroll
                for (int ks = 0; ks < 8; ks++) wgmma_rl_56(aq, h[4 * ks], h[4 * ks + 1], h[4 * ks + 2], h[4 * ks + 3], bq0 + ks * 128, ks != 0);
                WG_COMMIT();
                WG_WAIT(1);
                reg_fence<28>(av);
#pragma unroll
                for (int g = 0; g < 7; g++) {
                    vp[2 * g] = pack2(av[4 * g], av[4 * g + 1]); vp[2 * g + 1] = pack2(av[4 * g + 2], av[4 * g + 3]);
                    kvg[3584 + g * 32] = vp[2 * g]; kvg[3584 + 224 + g * 32] = vp[2 * g + 1];
                }
                warp_arrive(BAR(B_PUB + 1));
                PROFC(5);
                WG_FENCE();
#pragma unroll
                for (int ks = 8; ks < 28; ks++) wgmma_rl_56(aq, h[4 * ks], h[4 * ks + 1], h[4 * ks + 2], h[4 * ks + 3], bq0 + ks * 128, 1);
                WG_COMMIT();
                WAIT(B_PUB + 1, 0);
                const uint32_t rg = 8 * w + 2 * wi + ((lane >> 3) & 1);
                const uint32_t ko = sb + OFF_Y + Y_KOWN + rg * 896 + (lane & 7) * 16, qo = sb + OFF_Y + Y_Q + rg * 1024 + (lane >> 4) * 128 + (lane & 7) * 16;
#pragma unroll
                for (int g = 0; g < 6; g += 2) {
                    stsm4(ko + (g + (lane >> 4)) * 128, kp[2 * g], kp[2 * g + 1], kp[2 * g + 2], kp[2 * g + 3]);
                    stsm4(ko + (Y_VOWN - Y_KOWN) + (g + (lane >> 4)) * 128, vp[2 * g], vp[2 * g + 1], vp[2 * g + 2], vp[2 * g + 3]);
                }
                stsm4(ko + (lane >> 4) * (Y_VOWN - Y_KOWN) + 6 * 128, kp[12], kp[13], vp[12], vp[13]);
                WG_WAIT(0);
                reg_fence<28>(aq);
                __syncwarp();
                if (lane == 3) mbar_arrive(BAR(B_XFREE));
                if (lane < 3 && w == 1) mbar_arrive(BAR(B_EMPTY + lane));
                uint32_t qp[14];
#pragma unroll
                for (int i = 0; i < 14; i++) qp[i] = pack2(aq[2 * i], aq[2 * i + 1]);
                stsm4(qo, qp[0], qp[1], qp[2], qp[3]);
                stsm4(qo + 256, qp[4], qp[5], q < 2 ? qp[6] : 0u, q < 2 ? qp[7] : 0u);
                stsm4(qo + 512, q < 2 ? 0u : qp[6], q < 2 ? 0u : qp[7], qp[8], qp[9]);
                stsm4(qo + 768, qp[10], qp[11], qp[12], qp[13]);
                if (!sc) bar_sync(3, 256);
            }
        }
        PROFC(6);
        WAIT(B_KRFULL, 0);
        PROFC(7);
        if (RUN(2)) {
#pragma unroll 1
            for (int hf = sc; hf < 2; hf++) {
                COORDS
                float s[136];
                float na = 0.f, nb = 0.f;
                const float CS = 0.18898223650461361f * 1.4426950408889634f;
                const int kg0 = 8 * hf + 2 * wi;
                const int pmin = 16 - 8 * r - 4 * hf - wi;
                const float NEG = __int_as_float(0xFF800000);
                {
                    uint32_t F[8];
                    const uint32_t qa = sb + OFF_Y + Y_Q + (kg0 + ((lane >> 3) & 1)) * 1024 + (4 * w + (lane >> 4)) * 128 + (lane & 7) * 16;
                    ldsm4(qa, F); ldsm4(qa + 256, F + 4);
                    uint32_t ka = sb + OFF_Y + Y_K + kg0 * 896 + (3 * w + (lane >> 3)) * 128 + (lane & 7) * 16;
#pragma unroll
                    for (int g = 0; g < 34; g++) {
                        uint32_t B[4];
                        if (g >= 12 && g % 4 == 0) ka += __float_as_uint(s[4 * (g - 12)]) & p.zero;
                        ldsm4(ka + g * 896, B);
                        mma16816_first(s + 4 * g, F[0], F[1], F[2], F[3], B[0], B[1]);
                        mma16816_v(s + 4 * g, F[4], F[5], F[6], F[7], B[2], B[3]);
                    }
                    const bool c0 = 2 * q > lr, c1 = 2 * q + 1 > lr;
                    if (!c0) { s[0] = NEG; s[6] = NEG; }
                    if (!c1) { s[1] = NEG; s[7] = NEG; }
                    s[2] = NEG; s[3] = NEG;
                    if (c0) { s[128] = NEG; s[134] = NEG; }
                    if (c1) { s[129] = NEG; s[135] = NEG; }
                    s[132] = NEG; s[133] = NEG;
                    float ma = NEG, mb = NEG;
#pragma unroll
                    for (int pp = 0; pp < 17; pp++) {
                        const float* e = s + 8 * pp;
                        const float bias = pp < pmin ? NEG : 0.f;
                        ma = fmaxf(ma, fmaxf(fmaxf(e[0], e[1]), fmaxf(e[4], e[5])) + bias);
                        mb = fmaxf(mb, fmaxf(fmaxf(e[2], e[3]), fmaxf(e[6], e[7])) + bias);
                    }
                    ma = fmaxf(ma, __shfl_xor_sync(~0u, ma, 1)); mb = fmaxf(mb, __shfl_xor_sync(~0u, mb, 1));
                    ma = fmaxf(ma, __shfl_xor_sync(~0u, ma, 2)); mb = fmaxf(mb, __shfl_xor_sync(~0u, mb, 2));
                    na = -ma * CS; nb = -mb * CS;
                }
                PROFC(8 + 3 * hf);
                {
                    WAIT(B_VRFULL, 0);
                    float o[16] = {}, rs[4] = {};
                    uint32_t pk[2];
                    const uint32_t va = sb + OFF_Y + Y_VR + (kg0 + ((lane >> 3) & 1)) * 896 + (3 * w + (lane >> 4)) * 128 + (lane & 7) * 16;
#pragma unroll
                    for (int pp = 0; pp < 17; pp++) {
                        uint32_t B[8];
                        const uint32_t v = va + pp * 1792 + (pp == 16 || (pp >= 9 && kg0 + 2 * pp >= 32) ? Y_VOWN - 32 * 896 : 0);
                        ldsm4t(v, B); ldsm4t(v + 256, B + 4);
                        float e[8];
                        const float bias = __uint_as_float((pp < pmin ? 0xFF800000u : 0u) | ((pp < 2 ? B[0] : pk[pp & 1]) & p.zero));
#pragma unroll
                        for (int i = 0; i < 8; i++) e[i] = ex2(fmaf(s[8 * pp + i], CS, ((i & 2) ? nb : na) + bias));
                        const uint32_t p0 = pack2(e[0], e[1]), p1 = pack2(e[2], e[3]), p2 = pack2(e[4], e[5]), p3 = pack2(e[6], e[7]);
                        pk[pp & 1] = p3;
                        mma16816(rs, p0, p1, p2, p3, 0x3F803F80u, 0x3F803F80u);
#pragma unroll
                        for (int g = 0; g < 4; g++) mma16816(o + 4 * g, p0, p1, p2, p3, B[2 * g], B[2 * g + 1]);
                    }
                    PROFC(9 + 3 * hf);
                    const float ia = rcp(rs[0]), ib = rcp(rs[2]);
                    uint32_t* og = act + RB_O + hf * 14336 + (7 * j + 3 * w) * 256 + wi * 64 + lane;
#pragma unroll
                    for (int g = 0; g < 4; g++) {
                        if ((g == 3 - 3 * w) ? ((q >> 1) == w) : true) {
                            og[g * 256] = pack2(o[4 * g] * ia, o[4 * g + 1] * ia);
                            og[g * 256 + 32] = pack2(o[4 * g + 2] * ib, o[4 * g + 3] * ib);
                        }
                    }
                    warp_arrive(BAR(B_PUB + 2 + hf));
                    PROFC(10 + 3 * hf);
                }
            }
        }
        uint32_t x1p[14];
        COORDS
        constexpr uint64_t DT = dconst(1024, 128, 0);
        const int tile = opaque((lds1(sb + M_EPOCH) & 1) * 2 + w);
        if (RUN(4)) {
            float ac[28];
            const uint32_t ad = mkdesc(sb + (w ? OFF_Y + HALF : OFF_X), DT), bd = mkdesc(sb + OFF_X + HALF, DB128) + kh;
            WAIT(B_WOFULL, 0);
            WAIT(B_MOD1, 1);
            WAIT(B_GFULL + w, 0);
            PROFC(28);
            reg_def<28>(ac);
#pragma unroll 1
            for (int u = 0; u < 4; u++) {
                if (u == 2) WAIT(B_XFULL + 2 + w, 1);
                WG_FENCE();
#pragma unroll
                for (int i = 0; i < 7; i++) wgmma_ss_56<DT, DB128>(ac, ad + (7 * u + i) * 128, bd + (7 * u + i) * 128, (u | i) != 0);
            }
            WG_COMMIT();
            WG_WAIT(0);
            reg_fence<28>(ac);
            PROFC(14);
            __syncwarp();
            if (lane < 3) mbar_arrive(BAR(B_EMPTY + 4 - w + lane));
            if (lane < 3 && w == 0) mbar_arrive(BAR(B_EMPTY + lane));
            float ds[4] = {}, da[4] = {}, db[4] = {};
            uint32_t* xo = act + RB_X1 + tile * 14336 + 7 * j * 256 + wi * 64 + lane;
#pragma unroll
            for (int g = 0; g < 7; g++) {
                const float2 ga = *(const float2*)(smem + M_G + (8 * g + 2 * q) * 4);
                x1p[2 * g] = pack2(fmaf(ga.x, ac[4 * g], bf_lo(xr[2 * g])), fmaf(ga.y, ac[4 * g + 1], bf_hi(xr[2 * g])));
                x1p[2 * g + 1] = pack2(fmaf(ga.x, ac[4 * g + 2], bf_lo(xr[2 * g + 1])), fmaf(ga.y, ac[4 * g + 3], bf_hi(xr[2 * g + 1])));
                st_relaxed(xo + g * 256, nz(x1p[2 * g])); st_relaxed(xo + g * 256 + 32, nz(x1p[2 * g + 1]));
                mma1688(ds, x1p[2 * g], x1p[2 * g + 1], 0x3F803F80u);
                mma1688(da, x1p[2 * g], x1p[2 * g + 1], x1p[2 * g]);
                mma1688(db, x1p[2 * g], x1p[2 * g + 1], x1p[2 * g + 1]);
            }
            const int src = (lane & ~3) | (lr >> 1);
            const float qa = __shfl_sync(~0u, (lr & 1) ? da[1] : da[0], src), qb = __shfl_sync(~0u, (lr & 1) ? db[3] : db[2], src);
            const float kk = (q & 1) ? ((q & 2) ? qb : qa) : ((q & 2) ? ds[2] : ds[0]);
            st_relaxed(act + RB_ST + ((tile * 8 + j) * 64 + 16 * wi + lr + 4 * (q & 2)) * 2 + (q & 1), nz(__float_as_uint(kk)));
            __syncwarp();
            if (lane < 2) mbar_arrive(BAR(B_PUB + 4 + w));
        } else reg_def<14>(x1p);
        PROFC(15);
        uint32_t h2a[32], h2b[24];
        {
            const int fa = pass_f(fs, 0), fb = pass_f(fs, 1), fc = pass_f(fs, 2);
            uint32_t* h2g = act + RB_H2 + (8 * w + 2 * wi) * 32 + lane;
            const uint32_t a0 = mkdesc(sb + OFF_Y + w * HALF, DT);
            if (RUN(3)) {
                uint32_t ra2, na2, rb2, nb2;
                {
                    const uint32_t* sg = act + RB_ST + ((tile * 8 + 2 * q) * 64 + 16 * wi + lr) * 2;
                    uint2 u[4];
                    WAIT(B_GFULL + 2 + w, 0);
                    PROFC(16);
#pragma unroll
                    for (int i = 0; i < 4; i++) { const float2 v = lds2f(sb + OFF_X + X_STAT + w * 49152 + ((2 * q + (i >> 1)) * 64 + 16 * wi + lr + 8 * (i & 1)) * 8); u[i] = make_uint2(__float_as_uint(v.x), __float_as_uint(v.y)); }
                    while (__any_sync(~0u, min(min(min(u[0].x, u[0].y), min(u[1].x, u[1].y)), min(min(u[2].x, u[2].y), min(u[3].x, u[3].y))) < 1u - sc)) {
#pragma unroll
                        for (int i = 0; i < 4; i++) u[i] = ld_relaxed2(sg + (i >> 1) * 128 + (i & 1) * 16);
                    }
                    warp_arrive(BAR(B_EMPTY + 3 + 3 * w));
                    float v[4] = {__uint_as_float(u[0].x) + __uint_as_float(u[2].x), __uint_as_float(u[0].y) + __uint_as_float(u[2].y),
                                  __uint_as_float(u[1].x) + __uint_as_float(u[3].x), __uint_as_float(u[1].y) + __uint_as_float(u[3].y)};
#pragma unroll
                    for (int i = 0; i < 4; i++) { v[i] += __shfl_xor_sync(~0u, v[i], 1); v[i] += __shfl_xor_sync(~0u, v[i], 2); }
                    ln_coeffs(v[0] * (1.f / DM), v[1] * (1.f / DM), ra2, na2);
                    ln_coeffs(v[2] * (1.f / DM), v[3] * (1.f / DM), rb2, nb2);
                }
                const uint32_t ha = sb + OFF_Y + w * HALF + (lane >> 4) * 1024 + (2 * wi + ((lane >> 3) & 1)) * 128 + (lane & 7) * 16;
                const uint32_t sta = sb + M_ST + q * 16;
                const uint32_t* xg = act + RB_X1 + tile * 14336 + (lane >> 4) * 256 + wi * 64 + (lane & 15) * 4;
                uint32_t x[8];
                const uint32_t xs = sb + OFF_Y + w * HALF + (lane >> 4) * 1024 + wi * 256 + (lane & 15) * 16;
                uint4 st[2];
                auto load = [&](int s) {
                    if (s == 4) mbar_wait_c(BAR(B_XFULL + 4 + w), 1);
                    ldsm4(ha + s * 4096, x); ldsm4(ha + s * 4096 + 2048, x + 4);
                    st[0] = lds4(sta + s * 128); st[1] = lds4(sta + s * 128 + 64);
                };
                auto prep = [&](int s, uint32_t* f) {
                    if (__any_sync(~0u, min(min(min(x[0], x[1]), min(x[2], x[3])), min(min(x[4], x[5]), min(x[6], x[7]))) < 1u - sc)) {
                        WG_WAIT(0);
                        x1_fix(xg, xs, s);
                        ldsm4(ha + s * 4096, x); ldsm4(ha + s * 4096 + 2048, x + 4);
                    }
#pragma unroll
                    for (int i = 0; i < 2; i++) {
                        f[4 * i] = hfma2(hfma2(x[4 * i], ra2, na2), st[i].x, st[i].y); f[4 * i + 1] = hfma2(hfma2(x[4 * i + 1], rb2, nb2), st[i].x, st[i].y);
                        f[4 * i + 2] = hfma2(hfma2(x[4 * i + 2], ra2, na2), st[i].z, st[i].w); f[4 * i + 3] = hfma2(hfma2(x[4 * i + 3], rb2, nb2), st[i].z, st[i].w);
                    }
                    if (s < 13) load(s + 1);
                    stsm4(ha + s * 4096, f[0], f[1], f[2], f[3]); stsm4(ha + s * 4096 + 2048, f[4], f[5], f[6], f[7]);
                };
                float ac[128];
                uint32_t fr[3][8];
                uint64_t bd = (DB128 & ~0xFFFFFFFFull) | mkdesc(sb, DB128);
                reg_def<128>(ac);
                load(0);
                prep(0, fr[0]);
                PROFC(17);
#pragma unroll
                for (int s = 0; s < 14; s++) {
                    const uint32_t* f = fr[s % 3];
                    WAIT(B_FULL + g1_slot(s), s >= 7);
                    WG_FENCE();
                    wgmma_rl_256(ac, f[0], f[1], f[2], f[3], bd, s != 0);
                    wgmma_rl_256(ac, f[4], f[5], f[6], f[7], bd + 128, 1);
                    bd += s == 6 ? p.zero - 6 * 1024ull : 1024;
                    WG_COMMIT();
                    if (s < 13) prep(s + 1, fr[(s + 1) % 3]);
                    if (s > 0) { WG_WAIT(1); warp_arrive(BAR(B_EMPTY + g1_slot(s - 1))); }
                }
                fence_async_smem();
                PROFC(18);
                WG_WAIT(0);
                reg_fence<128>(ac);
                warp_arrive(BAR(B_EMPTY + 6));
#pragma unroll
                for (int g = 0; g < 16; g++) {
                    h2a[2 * g] = hmul2(pack2_relu(ac[4 * g], ac[4 * g + 1]), pack2(ac[64 + 4 * g], ac[64 + 4 * g + 1]));
                    h2a[2 * g + 1] = hmul2(pack2_relu(ac[4 * g + 2], ac[4 * g + 3]), pack2(ac[64 + 4 * g + 2], ac[64 + 4 * g + 3]));
                }
                bar_sync(1 + w, 128);
            } else reg_def<32>(h2a);
            PROFC(19);
            if (RUN(5)) {
                float ac[64];
                reg_def<64>(ac);
                const uint32_t bx = mkdesc(sb, dconst(8192, 1024, 1));
#pragma unroll kB
                for (int s = 0; s < 7; s++) {
                    WAIT(B_FULL + s, 0);
                    const uint32_t ad = a0 + s * 512, bd = bx + (slot_off(s) >> 4);
                    WG_FENCE();
#pragma unroll
                    for (int k = 0; k < 4; k++) wgmma_ss_128<DT, DB128>(ac, ad + k * 128, bd + k * 128, (s | k) != 0);
                    WG_COMMIT();
                    if (s == 1) {
#pragma unroll
                        for (int g = 0; g < 16; g++) { h2g[(fa / 8 + g) * 512] = h2a[2 * g]; h2g[(fa / 8 + g) * 512 + 32] = h2a[2 * g + 1]; }
                        warp_arrive(BAR(B_PUB + 6));
                    }
                    if (s > 0) { WG_WAIT(1); warp_arrive(BAR(B_EMPTY + s - 1)); }
                }
                WG_WAIT(0);
                reg_fence<64>(ac);
                warp_arrive(BAR(B_EMPTY + 6));
#pragma unroll
                for (int g = 0; g < 8; g++) {
                    h2b[2 * g] = hmul2(pack2_relu(ac[4 * g], ac[4 * g + 1]), pack2(ac[32 + 4 * g], ac[32 + 4 * g + 1]));
                    h2b[2 * g + 1] = hmul2(pack2_relu(ac[4 * g + 2], ac[4 * g + 3]), pack2(ac[32 + 4 * g + 2], ac[32 + 4 * g + 3]));
                }
            } else reg_def<16>(h2b);
            PROFC(27);
            if (RUN(6)) {
                float ac[32];
                reg_def<32>(ac);
                const uint32_t bx = mkdesc(sb, dconst(4096, 512, 2));
#pragma unroll kC
                for (int s = 0; s < 7; s++) {
                    WAIT(B_FULL + s, 1);
                    const uint32_t ad = a0 + s * 512, bd = bx + (slot_off(s) >> 4);
                    WG_FENCE();
#pragma unroll
                    for (int k = 0; k < 4; k++) wgmma_ss_64<DT, dconst(4096, 512, 2)>(ac, ad + k * 128, bd + k * 64, (s | k) != 0);
                    WG_COMMIT();
                    if (s == 1) {
#pragma unroll
                        for (int g = 0; g < 8; g++) { h2g[(fb / 8 + g) * 512] = h2b[2 * g]; h2g[(fb / 8 + g) * 512 + 32] = h2b[2 * g + 1]; }
                        warp_arrive(BAR(B_PUB + 7));
                    }
                    if (s > 0) { WG_WAIT(1); warp_arrive(BAR(B_EMPTY + s - 1)); }
                }
                WG_WAIT(0);
                reg_fence<32>(ac);
                __syncwarp();
                if (lane < 6) mbar_arrive(BAR(B_EMPTY + 6 + lane));
                PROFC(20);
#pragma unroll
                for (int g = 0; g < 4; g++) {
                    h2b[16 + 2 * g] = hmul2(pack2_relu(ac[4 * g], ac[4 * g + 1]), pack2(ac[16 + 4 * g], ac[16 + 4 * g + 1]));
                    h2b[16 + 2 * g + 1] = hmul2(pack2_relu(ac[4 * g + 2], ac[4 * g + 3]), pack2(ac[16 + 4 * g + 2], ac[16 + 4 * g + 3]));
                    h2g[(fc / 8 + g) * 512] = h2b[16 + 2 * g]; h2g[(fc / 8 + g) * 512 + 32] = h2b[16 + 2 * g + 1];
                }
                warp_arrive(BAR(B_PUB + 8));
                asm volatile("barrier.cluster.wait.aligned;" ::: "memory");
                if (lane == 0 && !sc) {
                    uint32_t rb;
                    asm volatile("mapa.shared::cluster.u32 %0, %1, %2;" : "=r"(rb) : "r"(BAR(B_PEER)), "r"(kh ^ 1));
                    asm volatile("mbarrier.arrive.relaxed.cluster.shared::cluster.b64 _, [%0];" ::"r"(rb) : "memory");
                }
            } else reg_def<8>(h2b + 16);
        }
        PROFC(21);
        if (RUN(7)) {
            float ac[56];
            reg_def<56>(ac);
            constexpr uint64_t DAN = dconst(2048, 128, 0);
            constexpr uint64_t DW = dconst(128, 512, 0);
            const uint32_t bx = mkdesc(sb, DW);
#pragma unroll
            for (int e = 0; e < 4; e++) {
                WAIT(B_FULL + e, 0);
                const uint64_t bd = ((DW & ~0xFFFFFFFFull) | bx) + (slot_off(e) >> 4);
                const uint32_t* hh = e < 2 ? h2a + 16 * e : h2b + 16 * (e - 2);
                WG_FENCE();
#pragma unroll
                for (int k = 0; k < (e < 3 ? 4 : 2); k++) wgmma_rl_112(ac, hh[4 * k], hh[4 * k + 1], hh[4 * k + 2], hh[4 * k + 3], bd + (k >> 1) * 512 + (k & 1) * 16, (e | k) != 0);
                WG_COMMIT();
                if (e > 0) { WG_WAIT(1); warp_arrive(BAR(B_EMPTY + e - 1)); }
            }
            PROFC(22);
            uint32_t ad = mkdesc(sb + 4 * 16384 + 8192 + w * 1024, DAN), bd = bx + 4 * 1024, fb_ = BAR(B_FULL + 4), eb_ = BAR(B_EMPTY + 3), par = sc;
#pragma unroll 1
            for (int e = 4; e < 25; e++) {
                mbar_wait_c(fb_, par);
                WG_FENCE();
                wgmma_ss_112<DAN, DW>(ac, ad, bd, 1);
                wgmma_ss_112<DAN, DW>(ac, ad + 256, bd + 16, 1);
                WG_COMMIT();
                WG_WAIT(1);
                warp_arrive(eb_);
                eb_ = fb_ + 8 * (B_EMPTY - B_FULL);
                ad += 1024; bd += 1024; fb_ += 8;
                if (e == 11 || e == 23) { ad -= 12 * 1024; bd -= 12 * 1024; fb_ -= 96; par = (par ^ 1) | sc; }
            }
            mbar_wait_cluster(BAR(B_PEER), sc);
            WG_WAIT(0);
            reg_fence<56>(ac);
            PROFC(24);
            uint32_t rdst, rbar;
            asm volatile("mapa.shared::cluster.u32 %0, %1, %2;" : "=r"(rdst) : "r"(sb + OFF_Y + (5 + w) * 16384 + t * 16), "r"(kh ^ 1 ^ sc));
            asm volatile("mapa.shared::cluster.u32 %0, %1, %2;" : "=r"(rbar) : "r"(BAR(B_XCH + w)), "r"(kh ^ 1 ^ sc));
#pragma unroll
            for (int g = 0; g < 7; g++) {
                const float v0 = ac[28 + 4 * g + 0], v1 = ac[28 + 4 * g + 1];
                const float v2 = ac[28 + 4 * g + 2], v3 = ac[28 + 4 * g + 3];
                if (!sc) asm volatile("st.async.shared::cluster.mbarrier::complete_tx::bytes.v4.f32 [%0], {%1,%2,%3,%4}, [%5];"
                             ::"r"(rdst + g * 2048), "f"(v0), "f"(v1), "f"(v2), "f"(v3), "r"(rbar) : "memory");
            }
            mbar_wait_cluster(BAR(B_XCH + w), sc);
            PROFC(25);
            bf16* og = (sc ? (bf16*)act : p.out + (size_t)128 * r * DM) + (size_t)ra * DM + 56 * j + 2 * q;
#pragma unroll
            for (int g = 0; g < 7; g++) {
                const uint4 rv = *(const uint4*)(smem + OFF_Y + (5 + w) * 16384 + t * 16 + g * 2048);
                const float2 gb = *(const float2*)(smem + M_G + 224 + (8 * g + 2 * q) * 4);
                const float v0 = ac[4 * g + 0] + __uint_as_float(rv.x), v1 = ac[4 * g + 1] + __uint_as_float(rv.y);
                const float v2 = ac[4 * g + 2] + __uint_as_float(rv.z), v3 = ac[4 * g + 3] + __uint_as_float(rv.w);
                *(uint32_t*)(og + 8 * g) = pack2(fmaf(gb.x, v0, bf_lo(x1p[2 * g])), fmaf(gb.y, v1, bf_hi(x1p[2 * g])));
                *(uint32_t*)(og + 8 * DM + 8 * g) = pack2(fmaf(gb.x, v2, bf_lo(x1p[2 * g + 1])), fmaf(gb.y, v3, bf_hi(x1p[2 * g + 1])));
            }
        }
        PROFC(26);
        bar_sync(1 + w, 128);
        if (wi == 0) warp_arrive(BAR(B_DONE));
        return;
    }
    helper_late(p, r, j, warp PROF_ARGS);
}

#undef act
typedef CUresult (*EncodeFn)(CUtensorMap*, CUtensorMapDataType, cuuint32_t, void*, const cuuint64_t*, const cuuint64_t*, const cuuint32_t*,
                             const cuuint32_t*, CUtensorMapInterleave, CUtensorMapSwizzle, CUtensorMapL2promotion, CUtensorMapFloatOOBfill);

static void make_map(EncodeFn fn, CUtensorMap* m, const void* ptr, uint64_t d0, uint64_t d1, uint64_t d2, uint64_t s1, uint64_t s2,
                     uint32_t b0, uint32_t b1, uint32_t b2, CUtensorMapSwizzle sw) {
    cuuint64_t dims[3] = {d0, d1, d2}, strides[2] = {s1, s2};
    cuuint32_t box[3] = {b0, b1, b2}, es[3] = {1, 1, 1};
    CUresult rc = fn(m, CU_TENSOR_MAP_DATA_TYPE_BFLOAT16, 3, (void*)ptr, dims, strides, box, es, CU_TENSOR_MAP_INTERLEAVE_NONE, sw,
                     CU_TENSOR_MAP_L2_PROMOTION_L2_128B, CU_TENSOR_MAP_FLOAT_OOB_FILL_NONE);
    (void)rc;
}

extern "C" void kernel_launch(void* const* d_in, const int* in_sizes, int n_in, void* d_out, int out_size) {
    (void)in_sizes; (void)n_in; (void)out_size;
    static EncodeFn fn = nullptr;
    static uint32_t* act_base = nullptr;
    if (!fn) {
        cudaDriverEntryPointQueryResult st;
        cudaGetDriverEntryPoint("cuTensorMapEncodeTiled", (void**)&fn, cudaEnableDefault, &st);
        void* a = nullptr;
        cudaGetSymbolAddress(&a, g_act);
        act_base = (uint32_t*)(((uintptr_t)a + 0xFFFFF) & ~(uintptr_t)0xFFFFF);
        cudaFuncSetAttribute(fused_block_kernel, cudaFuncAttributeMaxDynamicSharedMemorySize, SMEM_BYTES);
    }
    Params p;
    p.x = (const bf16*)d_in[0];
    const bf16* wqkv = (const bf16*)d_in[1];
    p.wqkv = wqkv;
    p.wop = (const bf16*)d_in[2];
    p.wg = (const bf16*)d_in[4];
    p.wu = (const bf16*)d_in[5];
    p.wd = (const bf16*)d_in[6];
    p.c = (const bf16*)d_in[7];
    p.wmod = (const bf16*)d_in[8];
    p.out = (bf16*)d_out;
    p.zero = 0;
    p.actb = act_base;
    make_map(fn, &p.wm, p.wmod, 2688, 448, 1, 5376, 5376 * 448, 16, 224, 1, CU_TENSOR_MAP_SWIZZLE_NONE);
    make_map(fn, &p.xm, p.x, 448, 2048, 1, 896, 896 * 2048, 64, 128, 1, CU_TENSOR_MAP_SWIZZLE_128B);
    make_map(fn, &p.qkv, wqkv, 1344, 448, 1, 2688, 2688 * 448, 64, 224, 1, CU_TENSOR_MAP_SWIZZLE_128B);
    make_map(fn, &p.wo, p.wop, 448, 448, 1, 896, 896 * 448, 64, 224, 1, CU_TENSOR_MAP_SWIZZLE_128B);
    make_map(fn, &p.ga, p.wg, 64, 448, 28, 3584, 128, 64, 32, 2, CU_TENSOR_MAP_SWIZZLE_128B);
    make_map(fn, &p.ua, p.wu, 64, 448, 28, 3584, 128, 64, 32, 2, CU_TENSOR_MAP_SWIZZLE_128B);
    make_map(fn, &p.gb, p.wg, 64, 448, 28, 3584, 128, 64, 64, 1, CU_TENSOR_MAP_SWIZZLE_128B);
    make_map(fn, &p.ub, p.wu, 64, 448, 28, 3584, 128, 64, 64, 1, CU_TENSOR_MAP_SWIZZLE_128B);
    make_map(fn, &p.gc, p.wg, 32, 448, 56, 3584, 64, 32, 64, 1, CU_TENSOR_MAP_SWIZZLE_64B);
    make_map(fn, &p.uc, p.wu, 32, 448, 56, 3584, 64, 32, 64, 1, CU_TENSOR_MAP_SWIZZLE_64B);
    make_map(fn, &p.dn, p.wd, 8, 1792, 56, 896, 16, 8, 32, 7, CU_TENSOR_MAP_SWIZZLE_NONE);
    fused_block_kernel<<<GRID, 384, SMEM_BYTES>>>(p);
}
```

```cpp
#include <cuda_runtime.h>
#include <cuda_bf16.h>
#include <cuda.h>
#include <stdint.h>

typedef __nv_bfloat16 bf16;

__device__ __forceinline__ void wgmma_rl_56(float* d, uint32_t a0, uint32_t a1, uint32_t a2, uint32_t a3, uint64_t db, int sd) {
  asm volatile("{\n.reg .pred p;\nsetp.ne.b32 p, %33, 0;\n"
    "wgmma.mma_async.sync.aligned.m64n56k16.f32.bf16.bf16 {%0,%1,%2,%3,%4,%5,%6,%7,%8,%9,%10,%11,%12,%13,%14,%15,%16,%17,%18,%19,%20,%21,%22,%23,%24,%25,%26,%27}, {%28,%29,%30,%31}, %32, p, 1, 1, 1;\n}\n"
    : "+f"(d[0]),"+f"(d[1]),"+f"(d[2]),"+f"(d[3]),"+f"(d[4]),"+f"(d[5]),"+f"(d[6]),"+f"(d[7]),"+f"(d[8]),"+f"(d[9]),"+f"(d[10]),"+f"(d[11]),"+f"(d[12]),"+f"(d[13]),"+f"(d[14]),"+f"(d[15]),"+f"(d[16]),"+f"(d[17]),"+f"(d[18]),"+f"(d[19]),"+f"(d[20]),"+f"(d[21]),"+f"(d[22]),"+f"(d[23]),"+f"(d[24]),"+f"(d[25]),"+f"(d[26]),"+f"(d[27])
    : "r"(a0), "r"(a1), "r"(a2), "r"(a3), "l"(db), "r"(sd));
}
template<uint64_t CA, uint64_t CB> __device__ __forceinline__ void wgmma_ss_56(float* d, uint32_t da, uint32_t db, int sd) {
  asm volatile("{\n.reg .pred p;\n.reg .b64 a, b;\nsetp.ne.b32 p, %30, 0;\nmov.b64 a, {%28, %31};\nmov.b64 b, {%29, %32};\n"
    "wgmma.mma_async.sync.aligned.m64n56k16.f32.bf16.bf16 {%0,%1,%2,%3,%4,%5,%6,%7,%8,%9,%10,%11,%12,%13,%14,%15,%16,%17,%18,%19,%20,%21,%22,%23,%24,%25,%26,%27}, a, b, p, 1, 1, 0, 1;\n}\n"
    : "+f"(d[0]),"+f"(d[1]),"+f"(d[2]),"+f"(d[3]),"+f"(d[4]),"+f"(d[5]),"+f"(d[6]),"+f"(d[7]),"+f"(d[8]),"+f"(d[9]),"+f"(d[10]),"+f"(d[11]),"+f"(d[12]),"+f"(d[13]),"+f"(d[14]),"+f"(d[15]),"+f"(d[16]),"+f"(d[17]),"+f"(d[18]),"+f"(d[19]),"+f"(d[20]),"+f"(d[21]),"+f"(d[22]),"+f"(d[23]),"+f"(d[24]),"+f"(d[25]),"+f"(d[26]),"+f"(d[27])
    : "r"(da), "r"(db), "r"(sd), "n"((uint32_t)(CA >> 32)), "n"((uint32_t)(CB >> 32)));
}
__device__ __forceinline__ void wgmma_rl_256(float* d, uint32_t a0, uint32_t a1, uint32_t a2, uint32_t a3, uint64_t db, int sd) {
  asm volatile("{\n.reg .pred p;\nsetp.ne.b32 p, %133, 0;\n"
    "wgmma.mma_async.sync.aligned.m64n256k16.f32.bf16.bf16 {%0,%1,%2,%3,%4,%5,%6,%7,%8,%9,%10,%11,%12,%13,%14,%15,%16,%17,%18,%19,%20,%21,%22,%23,%24,%25,%26,%27,%28,%29,%30,%31,%32,%33,%34,%35,%36,%37,%38,%39,%40,%41,%42,%43,%44,%45,%46,%47,%48,%49,%50,%51,%52,%53,%54,%55,%56,%57,%58,%59,%60,%61,%62,%63,%64,%65,%66,%67,%68,%69,%70,%71,%72,%73,%74,%75,%76,%77,%78,%79,%80,%81,%82,%83,%84,%85,%86,%87,%88,%89,%90,%91,%92,%93,%94,%95,%96,%97,%98,%99,%100,%101,%102,%103,%104,%105,%106,%107,%108,%109,%110,%111,%112,%113,%114,%115,%116,%117,%118,%119,%120,%121,%122,%123,%124,%125,%126,%127}, {%128,%129,%130,%131}, %132, p, 1, 1, 1;\n}\n"
    : "+f"(d[0]),"+f"(d[1]),"+f"(d[2]),"+f"(d[3]),"+f"(d[4]),"+f"(d[5]),"+f"(d[6]),"+f"(d[7]),"+f"(d[8]),"+f"(d[9]),"+f"(d[10]),"+f"(d[11]),"+f"(d[12]),"+f"(d[13]),"+f"(d[14]),"+f"(d[15]),"+f"(d[16]),"+f"(d[17]),"+f"(d[18]),"+f"(d[19]),"+f"(d[20]),"+f"(d[21]),"+f"(d[22]),"+f"(d[23]),"+f"(d[24]),"+f"(d[25]),"+f"(d[26]),"+f"(d[27]),"+f"(d[28]),"+f"(d[29]),"+f"(d[30]),"+f"(d[31]),"+f"(d[32]),"+f"(d[33]),"+f"(d[34]),"+f"(d[35]),"+f"(d[36]),"+f"(d[37]),"+f"(d[38]),"+f"(d[39]),"+f"(d[40]),"+f"(d[41]),"+f"(d[42]),"+f"(d[43]),"+f"(d[44]),"+f"(d[45]),"+f"(d[46]),"+f"(d[47]),"+f"(d[48]),"+f"(d[49]),"+f"(d[50]),"+f"(d[51]),"+f"(d[52]),"+f"(d[53]),"+f"(d[54]),"+f"(d[55]),"+f"(d[56]),"+f"(d[57]),"+f"(d[58]),"+f"(d[59]),"+f"(d[60]),"+f"(d[61]),"+f"(d[62]),"+f"(d[63]),"+f"(d[64]),"+f"(d[65]),"+f"(d[66]),"+f"(d[67]),"+f"(d[68]),"+f"(d[69]),"+f"(d[70]),"+f"(d[71]),"+f"(d[72]),"+f"(d[73]),"+f"(d[74]),"+f"(d[75]),"+f"(d[76]),"+f"(d[77]),"+f"(d[78]),"+f"(d[79]),"+f"(d[80]),"+f"(d[81]),"+f"(d[82]),"+f"(d[83]),"+f"(d[84]),"+f"(d[85]),"+f"(d[86]),"+f"(d[87]),"+f"(d[88]),"+f"(d[89]),"+f"(d[90]),"+f"(d[91]),"+f"(d[92]),"+f"(d[93]),"+f"(d[94]),"+f"(d[95]),"+f"(d[96]),"+f"(d[97]),"+f"(d[98]),"+f"(d[99]),"+f"(d[100]),"+f"(d[101]),"+f"(d[102]),"+f"(d[103]),"+f"(d[104]),"+f"(d[105]),"+f"(d[106]),"+f"(d[107]),"+f"(d[108]),"+f"(d[109]),"+f"(d[110]),"+f"(d[111]),"+f"(d[112]),"+f"(d[113]),"+f"(d[114]),"+f"(d[115]),"+f"(d[116]),"+f"(d[117]),"+f"(d[118]),"+f"(d[119]),"+f"(d[120]),"+f"(d[121]),"+f"(d[122]),"+f"(d[123]),"+f"(d[124]),"+f"(d[125]),"+f"(d[126]),"+f"(d[127])
    : "r"(a0), "r"(a1), "r"(a2), "r"(a3), "l"(db), "r"(sd));
}
template<uint64_t CA, uint64_t CB> __device__ __forceinline__ void wgmma_ss_128(float* d, uint32_t da, uint32_t db, int sd) {
  asm volatile("{\n.reg .pred p;\n.reg .b64 a, b;\nsetp.ne.b32 p, %66, 0;\nmov.b64 a, {%64, %67};\nmov.b64 b, {%65, %68};\n"
    "wgmma.mma_async.sync.aligned.m64n128k16.f32.bf16.bf16 {%0,%1,%2,%3,%4,%5,%6,%7,%8,%9,%10,%11,%12,%13,%14,%15,%16,%17,%18,%19,%20,%21,%22,%23,%24,%25,%26,%27,%28,%29,%30,%31,%32,%33,%34,%35,%36,%37,%38,%39,%40,%41,%42,%43,%44,%45,%46,%47,%48,%49,%50,%51,%52,%53,%54,%55,%56,%57,%58,%59,%60,%61,%62,%63}, a, b, p, 1, 1, 0, 1;\n}\n"
    : "+f"(d[0]),"+f"(d[1]),"+f"(d[2]),"+f"(d[3]),"+f"(d[4]),"+f"(d[5]),"+f"(d[6]),"+f"(d[7]),"+f"(d[8]),"+f"(d[9]),"+f"(d[10]),"+f"(d[11]),"+f"(d[12]),"+f"(d[13]),"+f"(d[14]),"+f"(d[15]),"+f"(d[16]),"+f"(d[17]),"+f"(d[18]),"+f"(d[19]),"+f"(d[20]),"+f"(d[21]),"+f"(d[22]),"+f"(d[23]),"+f"(d[24]),"+f"(d[25]),"+f"(d[26]),"+f"(d[27]),"+f"(d[28]),"+f"(d[29]),"+f"(d[30]),"+f"(d[31]),"+f"(d[32]),"+f"(d[33]),"+f"(d[34]),"+f"(d[35]),"+f"(d[36]),"+f"(d[37]),"+f"(d[38]),"+f"(d[39]),"+f"(d[40]),"+f"(d[41]),"+f"(d[42]),"+f"(d[43]),"+f"(d[44]),"+f"(d[45]),"+f"(d[46]),"+f"(d[47]),"+f"(d[48]),"+f"(d[49]),"+f"(d[50]),"+f"(d[51]),"+f"(d[52]),"+f"(d[53]),"+f"(d[54]),"+f"(d[55]),"+f"(d[56]),"+f"(d[57]),"+f"(d[58]),"+f"(d[59]),"+f"(d[60]),"+f"(d[61]),"+f"(d[62]),"+f"(d[63])
    : "r"(da), "r"(db), "r"(sd), "n"((uint32_t)(CA >> 32)), "n"((uint32_t)(CB >> 32)));
}
template<uint64_t CA, uint64_t CB> __device__ __forceinline__ void wgmma_ss_64(float* d, uint32_t da, uint32_t db, int sd) {
  asm volatile("{\n.reg .pred p;\n.reg .b64 a, b;\nsetp.ne.b32 p, %34, 0;\nmov.b64 a, {%32, %35};\nmov.b64 b, {%33, %36};\n"
    "wgmma.mma_async.sync.aligned.m64n64k16.f32.bf16.bf16 {%0,%1,%2,%3,%4,%5,%6,%7,%8,%9,%10,%11,%12,%13,%14,%15,%16,%17,%18,%19,%20,%21,%22,%23,%24,%25,%26,%27,%28,%29,%30,%31}, a, b, p, 1, 1, 0, 1;\n}\n"
    : "+f"(d[0]),"+f"(d[1]),"+f"(d[2]),"+f"(d[3]),"+f"(d[4]),"+f"(d[5]),"+f"(d[6]),"+f"(d[7]),"+f"(d[8]),"+f"(d[9]),"+f"(d[10]),"+f"(d[11]),"+f"(d[12]),"+f"(d[13]),"+f"(d[14]),"+f"(d[15]),"+f"(d[16]),"+f"(d[17]),"+f"(d[18]),"+f"(d[19]),"+f"(d[20]),"+f"(d[21]),"+f"(d[22]),"+f"(d[23]),"+f"(d[24]),"+f"(d[25]),"+f"(d[26]),"+f"(d[27]),"+f"(d[28]),"+f"(d[29]),"+f"(d[30]),"+f"(d[31])
    : "r"(da), "r"(db), "r"(sd), "n"((uint32_t)(CA >> 32)), "n"((uint32_t)(CB >> 32)));
}
template<uint64_t CA, uint64_t CB> __device__ __forceinline__ void wgmma_ss_112(float* d, uint32_t da, uint32_t db, int sd) {
  asm volatile("{\n.reg .pred p;\n.reg .b64 a, b;\nsetp.ne.b32 p, %58, 0;\nmov.b64 a, {%56, %59};\nmov.b64 b, {%57, %60};\n"
    "wgmma.mma_async.sync.aligned.m64n112k16.f32.bf16.bf16 {%0,%1,%2,%3,%4,%5,%6,%7,%8,%9,%10,%11,%12,%13,%14,%15,%16,%17,%18,%19,%20,%21,%22,%23,%24,%25,%26,%27,%28,%29,%30,%31,%32,%33,%34,%35,%36,%37,%38,%39,%40,%41,%42,%43,%44,%45,%46,%47,%48,%49,%50,%51,%52,%53,%54,%55}, a, b, p, 1, 1, 0, 1;\n}\n"
    : "+f"(d[0]),"+f"(d[1]),"+f"(d[2]),"+f"(d[3]),"+f"(d[4]),"+f"(d[5]),"+f"(d[6]),"+f"(d[7]),"+f"(d[8]),"+f"(d[9]),"+f"(d[10]),"+f"(d[11]),"+f"(d[12]),"+f"(d[13]),"+f"(d[14]),"+f"(d[15]),"+f"(d[16]),"+f"(d[17]),"+f"(d[18]),"+f"(d[19]),"+f"(d[20]),"+f"(d[21]),"+f"(d[22]),"+f"(d[23]),"+f"(d[24]),"+f"(d[25]),"+f"(d[26]),"+f"(d[27]),"+f"(d[28]),"+f"(d[29]),"+f"(d[30]),"+f"(d[31]),"+f"(d[32]),"+f"(d[33]),"+f"(d[34]),"+f"(d[35]),"+f"(d[36]),"+f"(d[37]),"+f"(d[38]),"+f"(d[39]),"+f"(d[40]),"+f"(d[41]),"+f"(d[42]),"+f"(d[43]),"+f"(d[44]),"+f"(d[45]),"+f"(d[46]),"+f"(d[47]),"+f"(d[48]),"+f"(d[49]),"+f"(d[50]),"+f"(d[51]),"+f"(d[52]),"+f"(d[53]),"+f"(d[54]),"+f"(d[55])
    : "r"(da), "r"(db), "r"(sd), "n"((uint32_t)(CA >> 32)), "n"((uint32_t)(CB >> 32)));
}
__device__ __forceinline__ void wgmma_rl_112(float* d, uint32_t a0, uint32_t a1, uint32_t a2, uint32_t a3, uint64_t db, int sd) {
  asm volatile("{\n.reg .pred p;\nsetp.ne.b32 p, %61, 0;\n"
    "wgmma.mma_async.sync.aligned.m64n112k16.f32.bf16.bf16 {%0,%1,%2,%3,%4,%5,%6,%7,%8,%9,%10,%11,%12,%13,%14,%15,%16,%17,%18,%19,%20,%21,%22,%23,%24,%25,%26,%27,%28,%29,%30,%31,%32,%33,%34,%35,%36,%37,%38,%39,%40,%41,%42,%43,%44,%45,%46,%47,%48,%49,%50,%51,%52,%53,%54,%55}, {%56,%57,%58,%59}, %60, p, 1, 1, 1;\n}\n"
    : "+f"(d[0]),"+f"(d[1]),"+f"(d[2]),"+f"(d[3]),"+f"(d[4]),"+f"(d[5]),"+f"(d[6]),"+f"(d[7]),"+f"(d[8]),"+f"(d[9]),"+f"(d[10]),"+f"(d[11]),"+f"(d[12]),"+f"(d[13]),"+f"(d[14]),"+f"(d[15]),"+f"(d[16]),"+f"(d[17]),"+f"(d[18]),"+f"(d[19]),"+f"(d[20]),"+f"(d[21]),"+f"(d[22]),"+f"(d[23]),"+f"(d[24]),"+f"(d[25]),"+f"(d[26]),"+f"(d[27]),"+f"(d[28]),"+f"(d[29]),"+f"(d[30]),"+f"(d[31]),"+f"(d[32]),"+f"(d[33]),"+f"(d[34]),"+f"(d[35]),"+f"(d[36]),"+f"(d[37]),"+f"(d[38]),"+f"(d[39]),"+f"(d[40]),"+f"(d[41]),"+f"(d[42]),"+f"(d[43]),"+f"(d[44]),"+f"(d[45]),"+f"(d[46]),"+f"(d[47]),"+f"(d[48]),"+f"(d[49]),"+f"(d[50]),"+f"(d[51]),"+f"(d[52]),"+f"(d[53]),"+f"(d[54]),"+f"(d[55])
    : "r"(a0), "r"(a1), "r"(a2), "r"(a3), "l"(db), "r"(sd));
}

constexpr int DM = 448;
constexpr int NCTA = 128;
#define MAPPING 1
#define GRID 128
#define PINGPONG 0
#define WIN 6
#define WIN_END 25
#define UNR_B 1
#define UNR_C 1
constexpr int kB = UNR_B, kC = UNR_C;
#define LIKELY(x) __builtin_expect(!!(x), 1)
#define PACE 1
#define PACE_END 6
#define GEMV_AT 2
#define NPRE 14
#define MAP_S 4
constexpr int SPIN_LIMIT = 1 << 22;

constexpr uint32_t OFF_X = 0, OFF_Y = 114688, OFF_MISC = 229376, SMEM_BYTES = 232448;
constexpr uint32_t Y_VR = 0, Y_K = 28672, Y_KOWN = 57344, Y_VOWN = 71680, Y_Q = 86016;
constexpr uint32_t HALF = 57344;
constexpr uint32_t X_STAT = 49152;
constexpr uint32_t M_BAR = OFF_MISC;
constexpr uint32_t M_ST = OFF_MISC + 512;
constexpr uint32_t M_G = OFF_MISC + 2304;
constexpr uint32_t M_EPOCH = OFF_MISC + 3040;
enum { B_XFULL = 0, B_FULLK = 7, B_FULLV = 8, B_FULLQ, B_KRFULL, B_VRFULL, B_WOFULL, B_XCH, B_MOD1 = 15, B_FULL = 16, B_WMFULL = 30,
       B_EMPTY = 32, B_XFREE = B_EMPTY + 12, B_GEMV, B_PEER,
       B_PUB = 47,
       B_WMFREE = 56, B_HRDY, B_GFULL = B_HRDY + 3, B_DONE = 31, B_DUMMY = B_GEMV };

__device__ uint32_t g_ticket;
__device__ __align__(128) uint32_t g_mod[8 * 6 * DM];
__device__ __align__(128) uint32_t g_flag[144 * 128];
constexpr int RB_WORDS = 262144, RB_KV = 0, RB_O = 57344, RB_X1 = 86016, RB_H2 = 143360, RB_ST = 258048;
__device__ __align__(128) uint32_t g_act[18 * RB_WORDS];
__device__ __align__(128) uint32_t g_wd[56 * 4 * 1792];
#define PROFH(id)
#define PROFH1(id)
#define PROFC(id)

struct alignas(64) Params {
    CUtensorMap wm, xm, qkv, wo, ga, ua, gb, ub, gc, uc, dn;
    const bf16 *x, *c, *wqkv, *wmod, *wg, *wu, *wd, *wop;
    bf16* out;
    uint32_t* actb;
    uint32_t zero;
};

__device__ __forceinline__ void mbar_init(uint32_t bar, int cnt) { asm volatile("mbarrier.init.shared::cta.b64 [%0], %1;" ::"r"(bar), "r"(cnt) : "memory"); }
__device__ __forceinline__ void mbar_expect_tx(uint32_t bar, uint32_t bytes) { asm volatile("mbarrier.arrive.expect_tx.shared::cta.b64 _, [%0], %1;" ::"r"(bar), "r"(bytes) : "memory"); }
__device__ __forceinline__ void mbar_arrive(uint32_t bar) { asm volatile("mbarrier.arrive.shared::cta.b64 _, [%0];" ::"r"(bar) : "memory"); }
__device__ __forceinline__ void mbar_wait(uint32_t bar, uint32_t parity) {
    uint32_t ok; int n = 0;
    do {
        asm volatile("{\n.reg .pred p;\nmbarrier.try_wait.parity.shared::cta.b64 p, [%1], %2;\nselp.u32 %0, 1, 0, p;\n}" : "=r"(ok) : "r"(bar), "r"(parity) : "memory");
        if (++n > SPIN_LIMIT) __trap();
    } while (!ok);
}
__device__ __forceinline__ void mbar_wait_c(uint32_t bar, uint32_t parity) {
    asm volatile("{\n.reg .pred p;\nWL:\nmbarrier.try_wait.parity.shared::cta.b64 p, [%0], %1, 0x989680;\n@!p bra WL;\n}" ::"r"(bar), "r"(parity) : "memory");
}
__device__ __forceinline__ void mbar_wait_cluster(uint32_t bar, uint32_t parity) {
    asm volatile("{\n.reg .pred p;\nWL:\nmbarrier.try_wait.parity.acquire.cluster.shared::cta.b64 p, [%0], %1, 0x989680;\n@!p bra WL;\n}" ::"r"(bar), "r"(parity) : "memory");
}
__device__ __forceinline__ void warp_arrive(uint32_t bar) {
    __syncwarp();
    asm volatile("{\n.reg .pred p;\nelect.sync _|p, 0xffffffff;\n@p mbarrier.arrive.shared::cta.b64 _, [%0];\n}" ::"r"(bar) : "memory");
}
__device__ __forceinline__ int opaque(int v) { return __shfl_sync(~0u, v, 0); }
__device__ __forceinline__ int fresh_tid() { int v; asm volatile("mov.u32 %0, %%tid.x;" : "=r"(v)); return v; }
__device__ __forceinline__ void bar_sync(int id, int n) { asm volatile("bar.sync %0, %1;" ::"r"(id), "r"(n) : "memory"); }
__device__ __forceinline__ void bar_arrive(int id, int n) { asm volatile("bar.arrive %0, %1;" ::"r"(id), "r"(n) : "memory"); }
__device__ __forceinline__ void fence_async_smem() { asm volatile("fence.proxy.async.shared::cta;" ::: "memory"); }
__device__ __forceinline__ void fence_async_global() { asm volatile("fence.proxy.async.global;" ::: "memory"); }
__device__ __forceinline__ void fence_gpu() { asm volatile("fence.release.gpu;" ::: "memory"); }
__device__ __forceinline__ void tma3(uint32_t dst, const CUtensorMap* m, int c0, int c1, int c2, uint32_t bar) {
    asm volatile("cp.async.bulk.tensor.3d.shared::cluster.global.mbarrier::complete_tx::bytes [%0], [%1, {%3, %4, %5}], [%2];"
                 ::"r"(dst), "l"(m), "r"(bar), "r"(c0), "r"(c1), "r"(c2) : "memory");
}
__device__ __forceinline__ void bulk_load(uint32_t dst, const void* src, uint32_t bytes, uint32_t bar) {
    asm volatile("cp.async.bulk.shared::cluster.global.mbarrier::complete_tx::bytes [%0], [%1], %2, [%3];" ::"r"(dst), "l"(src), "r"(bytes), "r"(bar) : "memory");
}
__device__ __forceinline__ void expect_e(uint32_t bar, uint32_t bytes) {
    asm volatile("{\n.reg .pred p;\nelect.sync _|p, 0xffffffff;\n@p mbarrier.arrive.expect_tx.shared::cta.b64 _, [%0], %1;\n}" ::"r"(bar), "r"(bytes) : "memory");
}
__device__ __forceinline__ void tma3_e(uint32_t dst, const CUtensorMap* m, int c0, int c1, int c2, uint32_t bar) {
    asm volatile("{\n.reg .pred p;\nelect.sync _|p, 0xffffffff;\n@p cp.async.bulk.tensor.3d.shared::cluster.global.mbarrier::complete_tx::bytes [%0], [%1, {%3, %4, %5}], [%2];\n}"
                 ::"r"(dst), "l"(m), "r"(bar), "r"(c0), "r"(c1), "r"(c2) : "memory");
}
__device__ __forceinline__ void bulk_e(uint32_t dst, const void* src, uint32_t bytes, uint32_t bar) {
    asm volatile("{\n.reg .pred p;\nelect.sync _|p, 0xffffffff;\n@p cp.async.bulk.shared::cluster.global.mbarrier::complete_tx::bytes [%0], [%1], %2, [%3];\n}"
                 ::"r"(dst), "l"(src), "r"(bytes), "r"(bar) : "memory");
}
__device__ __forceinline__ void init_e(uint32_t bar, int cnt) {
    asm volatile("{\n.reg .pred p;\nelect.sync _|p, 0xffffffff;\n@p mbarrier.init.shared::cta.b64 [%0], %1;\n}" ::"r"(bar), "r"(cnt) : "memory");
}
__device__ __forceinline__ void l2_prefetch_e(const void* src, uint32_t bytes) {
    asm volatile("{\n.reg .pred p;\nelect.sync _|p, 0xffffffff;\n@p cp.async.bulk.prefetch.L2.global [%0], %1;\n}" ::"l"(src), "r"(bytes) : "memory");
}
__device__ __forceinline__ uint32_t ld_relaxed(const uint32_t* p) { uint32_t v; asm volatile("ld.relaxed.gpu.global.u32 %0, [%1];" : "=r"(v) : "l"(p) : "memory"); return v; }
__device__ __forceinline__ void st_relaxed(uint32_t* p, uint32_t v) { asm volatile("st.relaxed.gpu.global.u32 [%0], %1;" ::"l"(p), "r"(v) : "memory"); }
__device__ __forceinline__ uint4 ld_relaxed4(const uint4* p) { uint4 v; asm volatile("ld.relaxed.gpu.global.v4.u32 {%0,%1,%2,%3}, [%4];" : "=r"(v.x), "=r"(v.y), "=r"(v.z), "=r"(v.w) : "l"(p) : "memory"); return v; }
__device__ __forceinline__ void st_relaxed4(uint4* p, uint4 v) { asm volatile("st.relaxed.gpu.global.v4.u32 [%0], {%1,%2,%3,%4};" ::"l"(p), "r"(v.x), "r"(v.y), "r"(v.z), "r"(v.w) : "memory"); }
__device__ __forceinline__ uint4 ldg_nc4(const void* p) { uint4 v; asm volatile("ld.global.nc.L1::no_allocate.v4.u32 {%0,%1,%2,%3}, [%4];" : "=r"(v.x), "=r"(v.y), "=r"(v.z), "=r"(v.w) : "l"(p)); return v; }
__device__ __forceinline__ uint32_t ldg_nc(const void* p) { uint32_t v; asm volatile("ld.global.nc.u32 %0, [%1];" : "=r"(v) : "l"(p)); return v; }
__device__ __forceinline__ uint32_t ld_acquire(const uint32_t* p) { uint32_t v; asm volatile("ld.acquire.gpu.global.u32 %0, [%1];" : "=r"(v) : "l"(p) : "memory"); return v; }
__device__ __forceinline__ uint4 lds4(uint32_t a) { uint4 v; asm volatile("ld.shared.v4.u32 {%0,%1,%2,%3}, [%4];" : "=r"(v.x), "=r"(v.y), "=r"(v.z), "=r"(v.w) : "r"(a) : "memory"); return v; }
__device__ __forceinline__ float2 lds2f(uint32_t a) { float2 v; asm volatile("ld.shared.v2.f32 {%0,%1}, [%2];" : "=f"(v.x), "=f"(v.y) : "r"(a) : "memory"); return v; }
__device__ __forceinline__ uint32_t lds1(uint32_t a) { uint32_t v; asm volatile("ld.shared.u32 %0, [%1];" : "=r"(v) : "r"(a) : "memory"); return v; }
__device__ __forceinline__ void sts4(uint32_t a, uint4 v) { asm volatile("st.shared.v4.u32 [%0], {%1,%2,%3,%4};" ::"r"(a), "r"(v.x), "r"(v.y), "r"(v.z), "r"(v.w) : "memory"); }
__device__ __forceinline__ void sts2(uint32_t a, uint32_t x, uint32_t y) { asm volatile("st.shared.v2.u32 [%0], {%1,%2};" ::"r"(a), "r"(x), "r"(y) : "memory"); }
__device__ __forceinline__ void sts1(uint32_t a, uint32_t v) { asm volatile("st.shared.u32 [%0], %1;" ::"r"(a), "r"(v) : "memory"); }
__device__ __forceinline__ void stsm4(uint32_t a, uint32_t r0, uint32_t r1, uint32_t r2, uint32_t r3) {
    asm volatile("stmatrix.sync.aligned.m8n8.x4.shared.b16 [%0], {%1,%2,%3,%4};" ::"r"(a), "r"(r0), "r"(r1), "r"(r2), "r"(r3));
}
__device__ __forceinline__ uint32_t pack2(float lo, float hi) { uint32_t r; asm("cvt.rn.bf16x2.f32 %0, %1, %2;" : "=r"(r) : "f"(hi), "f"(lo)); return r; }
__device__ __forceinline__ uint32_t pack2_relu(float lo, float hi) { uint32_t r; asm("cvt.rn.relu.bf16x2.f32 %0, %1, %2;" : "=r"(r) : "f"(hi), "f"(lo)); return r; }
__device__ __forceinline__ uint32_t hfma2(uint32_t a, uint32_t b, uint32_t c) { uint32_t r; asm("fma.rn.bf16x2 %0, %1, %2, %3;" : "=r"(r) : "r"(a), "r"(b), "r"(c)); return r; }
__device__ __forceinline__ uint32_t hmul2(uint32_t a, uint32_t b) { uint32_t r; asm("mul.rn.bf16x2 %0, %1, %2;" : "=r"(r) : "r"(a), "r"(b)); return r; }
__device__ __forceinline__ float bf_lo(uint32_t v) { return __uint_as_float(v << 16); }
__device__ __forceinline__ float bf_hi(uint32_t v) { return __uint_as_float(v & 0xFFFF0000u); }
__device__ __forceinline__ float bf_round(float v) { return bf_lo(pack2(v, 0.f)); }
__device__ __forceinline__ float ex2(float x) { float r; asm("ex2.approx.ftz.f32 %0, %1;" : "=f"(r) : "f"(x)); return r; }
__device__ __forceinline__ void mma16816(float* d, uint32_t a0, uint32_t a1, uint32_t a2, uint32_t a3, uint32_t b0, uint32_t b1) {
    asm("mma.sync.aligned.m16n8k16.row.col.f32.bf16.bf16.f32 {%0,%1,%2,%3}, {%4,%5,%6,%7}, {%8,%9}, {%0,%1,%2,%3};"
        : "+f"(d[0]), "+f"(d[1]), "+f"(d[2]), "+f"(d[3]) : "r"(a0), "r"(a1), "r"(a2), "r"(a3), "r"(b0), "r"(b1));
}
__device__ __forceinline__ void mma16816_first(float* d, uint32_t a0, uint32_t a1, uint32_t a2, uint32_t a3, uint32_t b0, uint32_t b1) {
    asm volatile("mma.sync.aligned.m16n8k16.row.col.f32.bf16.bf16.f32 {%0,%1,%2,%3}, {%4,%5,%6,%7}, {%8,%9}, {%10,%10,%10,%10};"
        : "=f"(d[0]), "=f"(d[1]), "=f"(d[2]), "=f"(d[3]) : "r"(a0), "r"(a1), "r"(a2), "r"(a3), "r"(b0), "r"(b1), "f"(0.f));
}
__device__ __forceinline__ void mma16816_v(float* d, uint32_t a0, uint32_t a1, uint32_t a2, uint32_t a3, uint32_t b0, uint32_t b1) {
    asm volatile("mma.sync.aligned.m16n8k16.row.col.f32.bf16.bf16.f32 {%0,%1,%2,%3}, {%4,%5,%6,%7}, {%8,%9}, {%0,%1,%2,%3};"
        : "+f"(d[0]), "+f"(d[1]), "+f"(d[2]), "+f"(d[3]) : "r"(a0), "r"(a1), "r"(a2), "r"(a3), "r"(b0), "r"(b1));
}
__device__ __forceinline__ void mma1688(float* d, uint32_t a0, uint32_t a1, uint32_t b0) {
    asm("mma.sync.aligned.m16n8k8.row.col.f32.bf16.bf16.f32 {%0,%1,%2,%3}, {%4,%5}, {%6}, {%0,%1,%2,%3};"
        : "+f"(d[0]), "+f"(d[1]), "+f"(d[2]), "+f"(d[3]) : "r"(a0), "r"(a1), "r"(b0));
}
__device__ __forceinline__ void ldsm4(uint32_t a, uint32_t* r) {
    asm volatile("ldmatrix.sync.aligned.m8n8.x4.shared.b16 {%0,%1,%2,%3}, [%4];" : "=r"(r[0]), "=r"(r[1]), "=r"(r[2]), "=r"(r[3]) : "r"(a));
}
__device__ __forceinline__ void ldsm4t(uint32_t a, uint32_t* r) {
    asm volatile("ldmatrix.sync.aligned.m8n8.x4.trans.shared.b16 {%0,%1,%2,%3}, [%4];" : "=r"(r[0]), "=r"(r[1]), "=r"(r[2]), "=r"(r[3]) : "r"(a));
}
__device__ __forceinline__ uint32_t nz(uint32_t v) { uint32_t r; asm("max.u32 %0, %1, 1;" : "=r"(r) : "r"(v)); return r; }
__device__ __forceinline__ float rcp(float x) { float r; asm("rcp.approx.ftz.f32 %0, %1;" : "=f"(r) : "f"(x)); return r; }
__device__ __forceinline__ uint2 ld_relaxed2(const void* p) { uint2 v; asm volatile("ld.relaxed.gpu.global.v2.u32 {%0,%1}, [%2];" : "=r"(v.x), "=r"(v.y) : "l"(p) : "memory"); return v; }
__device__ __forceinline__ void st_relaxed2(void* p, uint32_t x, uint32_t y) { asm volatile("st.relaxed.gpu.global.v2.u32 [%0], {%1,%2};" ::"l"(p), "r"(max(x, 1u)), "r"(max(y, 1u)) : "memory"); }
__host__ __device__ constexpr uint64_t dconst(uint32_t lbo, uint32_t sbo, uint32_t swz) {
    return ((uint64_t)(lbo >> 4) << 16) | ((uint64_t)(sbo >> 4) << 32) | ((uint64_t)swz << 62);
}
__device__ __forceinline__ uint32_t mkdesc(uint32_t addr, uint64_t c) { return (uint32_t)c | ((addr & 0x3FFFF) >> 4); }
#define WG_FENCE() asm volatile("wgmma.fence.sync.aligned;" ::: "memory")
#define WG_COMMIT() asm volatile("wgmma.commit_group.sync.aligned;" ::: "memory")
#define WG_WAIT(n) asm volatile("wgmma.wait_group.sync.aligned %0;" ::"n"(n) : "memory")
template <int N> __device__ __forceinline__ void reg_fence(float* d) {
#pragma unroll
    for (int i = 0; i < N; i++) asm volatile("" : "+f"(d[i])::"memory");
}
template <int N> __device__ __forceinline__ void reg_def(float* d) {
#pragma unroll
    for (int i = 0; i < N; i++) asm volatile("" : "=f"(d[i]));
}
template <int N> __device__ __forceinline__ void reg_def(uint32_t* d) {
#pragma unroll
    for (int i = 0; i < N; i++) asm volatile("" : "=r"(d[i]));
}
__device__ __forceinline__ bool is_unset(uint4 v) { return min(min(v.x, v.y), min(v.z, v.w)) == 0u; }
__device__ __forceinline__ uint4 nz4(uint32_t a, uint32_t b, uint32_t c, uint32_t d) { return make_uint4(max(a, 1u), max(b, 1u), max(c, 1u), max(d, 1u)); }
__device__ __forceinline__ void wait_flags(const uint32_t* p, uint32_t target, uint32_t mask) {
    int n = 0;
    while (~__ballot_sync(~0u, (int)(ld_relaxed(p) - target) >= 0) & mask) { if (++n > SPIN_LIMIT) __trap(); }
    asm volatile("fence.acquire.gpu;" ::: "memory");
}
__device__ __forceinline__ float silu_bf(uint32_t cbits) {
    const float c = __uint_as_float(cbits << 16);
    return bf_round(__fdividef(c, 1.f + fminf(ex2(-1.4426950408889634f * c), 1e30f)));
}
__device__ __forceinline__ void gemv_part(uint32_t wmbuf, int wp, int lane) {
    const uint32_t wa = wmbuf + wp * 512 + (8 * (lane >> 4) + (lane & 7)) * 32 + ((lane >> 3) & 1) * 16;
    float d[4] = {};
#pragma unroll
    for (int i = 0; i < 4; i++) {
        uint32_t A[4];
        const float2 v = lds2f(wmbuf + 28672 + (wp + 8 * i) * 32 + (lane & 3) * 8);
        ldsm4t(wa + (i < 3 || wp < 4 ? i : 0) * 4096, A);
        mma16816(d, A[0], A[1], A[2], A[3], __float_as_uint(v.x), __float_as_uint(v.y));
    }
    if ((lane & 3) == 0) {
        sts1(wmbuf + 29696 + (wp * 16 + (lane >> 2)) * 4, __float_as_uint(d[0]));
        sts1(wmbuf + 29696 + (wp * 16 + 8 + (lane >> 2)) * 4, __float_as_uint(d[2]));
    }
}
__device__ __forceinline__ uint32_t mod_word(float v, int col, uint32_t target) {
    v = bf_round(v);
    if ((col >= DM && col < 2 * DM) || (col >= 4 * DM && col < 5 * DM)) v += 1.f;
    return (pack2(v, 0.f) << 16) | (target & 0xFFFFu);
}
__device__ __forceinline__ const uint4* mod_src(int i, int r, int j, bool p2) {
    i = min(i, p2 ? 251 : 223);
    return (const uint4*)g_mod + (r & 7) * (6 * DM / 4) + (i < 224 ? (p2 ? 336 : 0) + i : (i < 238 ? 14 * j + i : 14 * j + i + 322));
}
__device__ __forceinline__ void mod_store(uint32_t sb, uint4 v, const uint4* src, int i) {
    const uint32_t tag = lds1(sb + M_EPOCH) + 1;
    while (__any_sync(~0u, (((v.x ^ tag) | (v.y ^ tag) | (v.z ^ tag) | (v.w ^ tag)) & 0xFFFFu) != 0u)) v = ld_relaxed4(src);
    if (i < 224) {
        const int isc = i >= 112, c4 = i - 112 * isc;
        const uint32_t a = sb + M_ST + (c4 >> 2) * 64 + (c4 & 1) * 32 + (c4 & 2) * 4 + (isc ? 0 : 4);
        sts1(a, __byte_perm(v.x, v.y, 0x7632));
        sts1(a + 16, __byte_perm(v.z, v.w, 0x7632));
    } else if (i < 252) {
        sts4(sb + M_G + (i - 224) * 16, make_uint4(v.x & 0xFFFF0000u, v.y & 0xFFFF0000u, v.z & 0xFFFF0000u, v.w & 0xFFFF0000u));
    }
}
__device__ __forceinline__ int pass_f(int fs, int ps) { return 224 * fs + ((fs & 1) ? (ps == 0 ? 96 : ps == 1 ? 32 : 0) : (ps == 0 ? 0 : ps == 1 ? 128 : 192)); }
__device__ __forceinline__ constexpr uint32_t slot_off(int l) { return l * 16384; }
__device__ __forceinline__ constexpr int g1_slot(int s) { return s % 7; }
__device__ __noinline__ void x1_fix(const uint32_t* g, uint32_t sa, int s) {
#pragma unroll 1
    for (int k = 4 * s; k < 4 * s + 4;) {
        const uint4 v = ld_relaxed4((const uint4*)(g + k * 256));
        sts4(sa + k * 1024, v);
        k += 2 * __all_sync(~0u, min(min(v.x, v.y), min(v.z, v.w)) != 0u);
    }
    __syncwarp();
}
__device__ __forceinline__ void ln_coeffs(float mean, float msq, uint32_t& r2, uint32_t& n2) {
    const float rs = bf_round(rsqrtf(fmaxf(msq - mean * mean, 0.f) + 1e-5f));
    r2 = pack2(rs, rs);
    n2 = pack2(-mean * rs, -mean * rs);
}

#define LOADW bulk_e(dst, g_wd + (size_t)((f >> 5) * 4 + nq) * 1792, 7168, bar);
template <int sec> __device__ __forceinline__ void ring_loader(const Params& p, uint32_t sb_, int r_, int j_, int lane) {
    const uint32_t sb = opaque(sb_);
    const int r = opaque(r_), j = opaque(j_), nq = j >> 1, fs = 4 * (j & 1) + nq;
    const int fa = pass_f(fs, 0), fb = pass_f(fs, 1), fc = pass_f(fs, 2);
    const uint32_t* h2src = (const uint32_t*)__shfl_sync(~0u, (unsigned long long)(p.actb + (size_t)r * RB_WORDS + RB_H2), 0);
    const CUtensorMap* gmap = (const CUtensorMap*)__shfl_sync(~0u, (unsigned long long)(&p.ga + sec), 0);
#define BAR(i) (sb + M_BAR + 8 * (i))
#define kh (j & 1)
            int sl = 0;
#pragma unroll 1
            for (int s = 0; s < 28; s++) {
                if (s == 7) { wait_flags(g_flag + (8 * r + j) * 128 + 96 + lane, lds1(sb + M_EPOCH) + 1, 0xFFFFu); fence_async_global(); }
                const int ps = s < 14 ? 0 : s < 21 ? 1 : 2;
                const uint32_t half = ps < 2 ? 8192 : 4096;
                const int sp = sl;
                if (s >= PACE && s < PACE_END) mbar_wait(BAR(B_FULL + s - PACE), 0);
                mbar_wait(BAR(B_EMPTY + sp), (s >= 7 && s < 14) || s >= 21);
                expect_e(BAR(B_FULL + sp), half);
                tma3_e(sb + slot_off(sp) + sec * half, gmap + 2 * ps, 0, ps ? 64 * sl : 32 * s, ps == 0 ? fa >> 6 : ps == 1 ? fb >> 6 : fc >> 5, BAR(B_FULL + sp));
                sl = sl == 6 ? 0 : sl + 1;
            }
            if (!sec) PROFH(3);
#pragma unroll 1
            for (int e = 0; e < 4; e++) {
                const uint32_t dst = sb + slot_off(e) + sec * 8192, bar = BAR(B_FULL + e);
                const int f = (e < 2 ? fa + 64 * e : e == 2 ? fb : fc) + 32 * sec;
                mbar_wait(BAR(B_EMPTY + e), 0);
                expect_e(bar, e == 3 && sec ? 0 : 7168);
                if (!(e == 3 && sec)) { LOADW }
            }
            sl = 4;
            int e = 4;
#pragma unroll 1
            for (int grp = 0; grp < 9; grp++) {
                const int ps = grp >= 6 ? 2 : grp >= 3 ? 1 : 0;
                int sidx = grp - 3 * ps;
                if (sec && sidx == 0) { mbar_wait(BAR(B_HRDY + ps), 0); fence_async_global(); }
                sidx += sidx >= nq;
                int f = pass_f(4 * kh + sidx, ps);
#pragma unroll 1
                for (int k = 4 >> ps; k > 0; k--, e++, f += 32) {
                    const uint32_t dst = sb + slot_off(sl), bar = BAR(B_FULL + sl);
                    mbar_wait(BAR(B_EMPTY + sl), e >= 12 && e < 24);
                    if (e < WIN_END && e >= WIN) mbar_wait(BAR(B_FULL + (sl >= WIN ? sl - WIN : sl + 12 - WIN)), e - WIN >= 12);
                    expect_e(bar, sec ? 8192 : 7168);
                    if (!sec) { LOADW }
                    else bulk_e(dst + 8192, h2src + f * 64, 8192, bar);
                    sl = sl == 11 ? 0 : sl + 1;
                }
            }
            if (!sec) PROFH(4);
}

#define PROF_PARAMS
#define PROF_ARGS
__device__ __noinline__ void helper_late(const Params& p, int r_, int j_, int warp_ PROF_PARAMS) {
    extern __shared__ __align__(1024) unsigned char smem[];
    const uint32_t sb = (uint32_t)__cvta_generic_to_shared(smem);
    const int r = opaque(r_), j = opaque(j_), warp = opaque(warp_), nq = j >> 1, b = 8 * r + j;
    uint32_t* const act = (uint32_t*)__shfl_sync(~0u, (unsigned long long)(p.actb + (size_t)r * RB_WORDS), 0);
    {
        const int lane = fresh_tid() & 31;
        const uint32_t target = lds1(sb + M_EPOCH) + 1;
        if (warp == 8) { expect_e(BAR(B_XCH), 14336); expect_e(BAR(B_XCH + 1), 14336); }
            if (warp == 9) {
#pragma unroll 1
                for (int kv = 0; kv < 2; kv++) {
                    mbar_wait(BAR(B_PUB + kv), 0);
                    wait_flags(g_flag + b * 128 + lane, target, (r >= 2 ? 6u : r == 1 ? 2u : 0u) << (8 * kv));
                    fence_async_global();
                    const uint32_t dst = sb + OFF_Y + (kv ? Y_VR : Y_K);
                    expect_e(BAR(B_KRFULL + kv), r >= 2 ? 28672 : r == 1 ? 14336 : 0);
                    if (r >= 2) bulk_e(dst, act - 2 * RB_WORDS + RB_KV + j * 7168 + kv * 3584, 14336, BAR(B_KRFULL + kv));
                    if (r >= 1) bulk_e(dst + 14336, act - RB_WORDS + RB_KV + j * 7168 + kv * 3584, 14336, BAR(B_KRFULL + kv));
                }
            } else if (warp == 8) {
                uint4 v[8];
                mbar_wait(BAR(B_WOFULL), 0);
#pragma unroll
                for (int k = 0; k < 8; k++) v[k] = ld_relaxed4(mod_src(lane + 32 * k, r, j, true));
#pragma unroll
                for (int k = 0; k < 8; k++) mod_store(sb, v[k], mod_src(lane + 32 * k, r, j, true), lane + 32 * k);
                warp_arrive(BAR(B_MOD1));
            } else if (warp == 11) {
                if (kh == 1 && r < 14) {
                    const uint32_t wmbuf = sb + OFF_X + HALF;
                    const int mcol = 2 * DM + 32 * (4 * r + nq);
                    mbar_wait(BAR(B_XFREE), 0);
#pragma unroll 1
                    for (int k = 0; k < 4; k++) tma3_e(wmbuf + k * 7168, &p.wm, mcol + (k >> 1) * 16, (k & 1) * 224, 0, BAR(B_WMFULL));
#pragma unroll 1
                    for (int wd = lane; wd < 224; wd += 32) {
                        const uint32_t cb = __ldg((const uint32_t*)p.c + wd);
                        sts1(wmbuf + 28672 + (wd >> 3) * 32 + (wd & 3) * 8 + (wd & 4), pack2(silu_bf(cb & 0xFFFFu), silu_bf(cb >> 16)));
                    }
                    __syncwarp();
                    mbar_wait(BAR(B_WMFULL), 0);
                    const uint32_t wa = wmbuf + (8 * (lane >> 4) + (lane & 7)) * 32 + ((lane >> 3) & 1) * 16;
                    float d[2][4] = {};
#pragma unroll 4
                    for (int ks = 0; ks < 28; ks++) {
                        uint32_t A[8];
                        ldsm4t(wa + ks * 512, A); ldsm4t(wa + 14336 + ks * 512, A + 4);
                        const float2 v = lds2f(wmbuf + 28672 + ks * 32 + (lane & 3) * 8);
                        mma16816(d[0], A[0], A[1], A[2], A[3], __float_as_uint(v.x), __float_as_uint(v.y));
                        mma16816(d[1], A[4], A[5], A[6], A[7], __float_as_uint(v.x), __float_as_uint(v.y));
                    }
                    const int q = lane & 3, col = mcol + 8 * q + (lane >> 2);
                    const uint32_t word = mod_word(q == 0 ? d[0][0] : q == 1 ? d[0][2] : q == 2 ? d[1][0] : d[1][2], col, target);
#pragma unroll
                    for (int i = 0; i < 8; i++) st_relaxed(g_mod + i * 6 * DM + col, word);
                }
                warp_arrive(BAR(B_WMFREE));
                mbar_wait(BAR(B_VRFULL), 0);
                l2_prefetch_e((const char*)p.wg + (size_t)b * 12544, 12544);
                l2_prefetch_e((const char*)p.wu + (size_t)b * 12544, 12544);
#pragma unroll 1
                for (int k = 0; k < (r < 12 ? 2 : 1); k++) {
                    const int u = 28 * kh + r + 16 * k;
                    expect_e(BAR(B_XFULL + k), 7168);
                    tma3_e(sb + OFF_Y + 102400, &p.dn, 0, 32 * u, 7 * j, BAR(B_XFULL + k));
                    tma3_e(sb + OFF_Y + 102400 + 3584, &p.dn, 0, 32 * u, 7 * (j ^ 1), BAR(B_XFULL + k));
                    mbar_wait(BAR(B_XFULL + k), 1);
                    asm volatile("{\n.reg .pred p;\nelect.sync _|p, 0xffffffff;\n@p cp.async.bulk.global.shared::cta.bulk_group [%0], [%1], 7168;\n"
                                 "cp.async.bulk.commit_group;\ncp.async.bulk.wait_group 0;\n}" ::"l"(g_wd + (size_t)(u * 4 + nq) * 1792), "r"(sb + OFF_Y + 102400) : "memory");
                    __syncwarp();
                }
                warp_arrive(BAR(B_FULLK));
                fence_gpu();
                if (lane < 16) st_relaxed(g_flag + (8 * lane + j) * 128 + 96 + r, target);
            }
        if (warp == 8 || warp == 11) {
            const int sec = warp == 11;
            if (sec) ring_loader<1>(p, sb, r, j, lane); else ring_loader<0>(p, sb, r, j, lane);
            mbar_wait(BAR(B_DONE), 0);
        } else if (warp == 9) {
#pragma unroll
            for (int ev = 0; ev < 4; ev++) { expect_e(BAR(B_GFULL + ev), ev < 2 ? HALF / 2 : 16384 + 4096); expect_e(BAR(B_XFULL + 2 + ev), ev < 2 ? HALF / 2 : HALF - 16384); }
            mbar_wait(BAR(B_PUB + 2), 0);
            const uint32_t* fp = g_flag + b * 128 + 32 + lane;
            const int par = (target - 1) & 1;
#pragma unroll 1
            for (int n = 0, ev = 0; ev < 4; n++) {
                if (ev == 1) mbar_wait(BAR(B_PUB + 3), 0);
                uint32_t ok = __ballot_sync(~0u, (int)(ld_relaxed(fp) - target) >= 0) >> (8 * ev);
                while ((ok & 0xFFu) == 0xFFu) {
                    if (ev == 1) mbar_wait(BAR(B_FULLK), 1);
                    asm volatile("fence.acquire.gpu;" ::: "memory");
                    fence_async_global();
                    const int tile = (ev & 1) + (ev >> 1) * par * 2;
                    const uint32_t dst = sb + (ev == 0 ? OFF_X : OFF_Y + (ev & 1) * HALF), first = ev < 2 ? HALF / 2 : 16384;
                    const char* src = (const char*)(act + RB_O + ((ev >> 1) * 2 + tile) * 14336);
                    if (ev >= 2) bulk_e(sb + OFF_X + X_STAT + (ev & 1) * 49152, act + RB_ST + tile * 1024, 4096, BAR(B_GFULL + ev));
                    bulk_e(dst, src, first, BAR(B_GFULL + ev));
                    bulk_e(dst + first, src + first, HALF - first, BAR(B_XFULL + 2 + ev));
                    if (ev) PROFH(4 + ev);
                    ev++; ok >>= 8;
                }
                if (n > SPIN_LIMIT) __trap();
            }
            mbar_wait(BAR(B_XFULL + 5), 1);
#pragma unroll 1
            for (int hf = 0; hf < 2; hf++) {
                const int tile = (par ^ 1) * 2 + hf;
                uint4* xz = (uint4*)(act + RB_X1 + tile * 14336 + j * 1792) + lane;
#pragma unroll
                for (int i = 0; i < 14; i++) xz[i * 32] = make_uint4(0, 0, 0, 0);
                ((uint4*)(act + RB_ST + (tile * 8 + j) * 128))[lane] = make_uint4(0, 0, 0, 0);
            }
#pragma unroll 1
            for (int ps = 0; ps < 3; ps++) {
                mbar_wait(BAR(B_PUB + 6 + ps), 0);
                wait_flags(g_flag + b * 128 + 64 + lane, target, (0x55u << kh) << (8 * ps));
                warp_arrive(BAR(B_HRDY + ps));
                PROFH(9 + ps);
            }
        } else {
#pragma unroll 1
            for (int k = 0; k < 9; k++) {
                uint32_t* fp = k < 2 ? g_flag + (b + 8 * lane) * 128 + k * 8 + lane : g_flag + (8 * r + lane) * 128 + 16 + k * 8 + j;
                mbar_wait(BAR(B_PUB + k), 0);
                if (k != 4 && k != 5) fence_gpu();
                if (k < 2 ? (lane == 1 || lane == 2) : lane < 8) st_relaxed(fp, target);
                if (k >= 3 && k <= 5) PROFH(k - 3);
            }
        }
    }
}

__global__ void __cluster_dims__(2, 1, 1) __launch_bounds__(384, 1) fused_block_kernel(const __grid_constant__ Params p) {
    extern __shared__ __align__(1024) unsigned char smem[];
    const uint32_t sb = (uint32_t)__cvta_generic_to_shared(smem);
    const int tid = threadIdx.x, lane = tid & 31, warp = __shfl_sync(~0u, tid >> 5, 0);
    const int m = blockIdx.x >> 1;
    int r, nq;
    if (m < 4) { r = 15; nq = m; }
    else if (m < 36) { r = (m - 4) & 7; nq = (m - 4) >> 3; }
    else { nq = (m - 36) / 7; r = m - 28 - 7 * nq; }
    const int j = opaque(2 * nq + (blockIdx.x & 1)), b = 8 * r + j, fs = 4 * kh + nq;
#define act (p.actb + (size_t)r * RB_WORDS)
    constexpr uint32_t sc = 0;
    if (lane == 0 && warp < 9 && warp != 6 && warp != 7) {
        const int i0 = warp == 8 ? 0 : 8 + 8 * warp, cnt = warp == 0 || warp == 8 ? 1 : warp < 3 ? 2 : 8;
#pragma unroll
        for (int k = 0; k < 8; k++) if (i0 + k != B_WMFULL) mbar_init(BAR(i0 + k), cnt);
        asm volatile("fence.mbarrier_init.release.cluster;" ::: "memory");
        fence_async_smem();
    }

    if (warp >= 8) {
        const int lane = fresh_tid() & 31;
        const bool early = kh == 0, gemv = r < 14;
        const int mcol = early ? 16 * (4 * r + nq) : 2 * DM + 32 * (4 * r + nq);
        const uint32_t wmbuf = sb + OFF_Y + HALF;
        asm volatile("setmaxnreg.dec.sync.aligned.u32 56;");
        if (warp == 9) {
#pragma unroll
            for (int i = 56; i < 64; i++) init_e(BAR(i), 1);
            fence_async_smem();
        }
        if (warp == 8) { init_e(BAR(B_WMFULL), 1); fence_async_smem(); }
        bar_arrive(0, 384);
        asm volatile("barrier.cluster.arrive.relaxed.aligned;" ::: "memory");
        if (warp == 8) {
            if (!sc) {
                expect_e(BAR(B_WMFULL), gemv ? 28672 >> early : 0);
                if (early && gemv) { tma3_e(wmbuf, &p.wm, mcol, 0, 0, BAR(B_WMFULL)); tma3_e(wmbuf + 7168, &p.wm, mcol, 224, 0, BAR(B_WMFULL)); }
#pragma unroll 1
                for (int kb = 0; kb < 7; kb++) {
                    expect_e(BAR(B_XFULL + kb), 16384);
                    tma3_e(sb + OFF_X + kb * 16384, &p.xm, 64 * kb, 128 * r, 0, BAR(B_XFULL + kb));
                }
            }
#pragma unroll 1
            for (int mt = 0; mt < 4; mt++) {
                if (mt == 1) bar_sync(9, 384);
                if (mt == 3) mbar_wait(BAR(B_WMFREE), 0);
                if (mt) mbar_wait(BAR(mt == 1 ? B_MOD1 : mt == 2 ? B_XFREE : B_VRFULL), 0);
                const uint32_t bar = BAR(mt == 3 ? B_WOFULL : B_FULLK + mt), dst = sb + (mt < 2 ? OFF_Y : OFF_X) + (mt & 1) * HALF;
                const int c0 = (mt < 2 ? DM + DM * mt : 0) + 56 * j - 8 * kh;
                if (!sc) {
                    expect_e(bar, HALF);
                    tma3_e(dst, mt == 3 ? &p.wo : &p.qkv, c0, 0, 0, bar);
                    tma3_e(dst + HALF / 2, mt == 3 ? &p.wo : &p.qkv, c0, 224, 0, bar);
                }
            }
        } else {
            if (warp == 10 && !sc) l2_prefetch_e((const char*)p.wqkv + (size_t)b * 9408, 9408);
            bar_sync(9, 384);
            if (sc) return;
            if (warp == 11 && early) {
                const uint32_t target = lds1(sb + M_EPOCH) + 1;
                mbar_wait(BAR(B_GEMV), 0);
                float sum = 0.f;
#pragma unroll
                for (int i = 0; i < 8; i++) sum += *(const float*)(smem + OFF_Y + HALF + 29696 + (i * 16 + (lane & 15)) * 4);
                uint32_t* mg = g_mod + mcol + (lane & 15) + (lane >> 4) * 4 * 6 * DM;
                const uint32_t word = mod_word(sum, mcol, target);
                if (gemv) { st_relaxed(mg, word); st_relaxed(mg + 6 * DM, word); st_relaxed(mg + 12 * DM, word); st_relaxed(mg + 18 * DM, word); }
            }
        }
    }
    if (LIKELY(warp < 8)) {
        const int w = warp >> 2, wi = warp & 3;
#define COORDS const int t = fresh_tid() & 127, lane = t & 31, q = lane & 3, lr = lane >> 2, ra = 64 * w + 16 * wi + lr; \
        const uint32_t lx = (lane >> 4) ^ (lane & 7), mrow = (64 * w + 16 * wi + ((lane >> 3) & 1) * 8 + (lane & 7)) * 128; \
        (void)q; (void)lr; (void)ra; (void)lx; (void)mrow;
        const int sid = 2 * (j & 3) + w;
#define RUN(k) (!sc || sid == (k))
#define WAIT(i, par) mbar_wait_c(BAR(i), (par) | sc)
        constexpr uint64_t DB128 = dconst(4096, 1024, 1);
        {
            const int wd = fresh_tid();
            const uint32_t cb = wd < 224 ? __ldg((const uint32_t*)p.c + wd) : 0u;
            if (wd == 255 && !sc) sts1(sb + M_EPOCH, atomicAdd(&g_ticket, 1u) / NCTA);
            sts1(sb + OFF_Y + HALF + 28672 + (wd >> 3) * 32 + (wd & 3) * 8 + (wd & 4), pack2(silu_bf(cb & 0xFFFFu), silu_bf(cb >> 16)));
        }
        bar_arrive(9, 384);
        bar_sync(0, 384);
        asm volatile("barrier.cluster.arrive.relaxed.aligned;" ::: "memory");
        asm volatile("setmaxnreg.inc.sync.aligned.u32 224;");
        PROFC(0);
        uint32_t xr[16];
        {
            COORDS
            uint32_t h[112];
            uint32_t ra2, na2, rb2, nb2;
            const int mi = min(128 * w + t, 223);
            const uint4* msrc = mod_src(mi, r, j, false);
            uint4 mv;
            {
                float ds[4] = {}, da[2][4] = {}, db[2][4] = {};
                const uint32_t ONE2 = 0x3F803F80u;
#pragma unroll
                for (int kb = 0; kb < 7; kb++) {
                    if (kb == GEMV_AT && kh == 0) { WAIT(B_WMFULL, 0); gemv_part(sb + OFF_Y + HALF, warp, lane); warp_arrive(BAR(B_GEMV)); }
                    WAIT(B_XFULL + kb, 0);
#pragma unroll
                    for (int k4 = 0; k4 < 4; k4++) ldsm4(sb + OFF_X + mrow + kb * 16384 + (((2 * k4) ^ lx) << 4), h + 16 * kb + 4 * k4);
#pragma unroll
                    for (int k4 = 0; k4 < 4; k4++) {
                        const uint32_t* f = h + 16 * kb + 4 * k4;
                        mma16816(ds, f[0], f[1], f[2], f[3], ONE2, ONE2);
                        mma1688(da[0], f[0], f[1], f[0]); mma1688(db[0], f[0], f[1], f[1]);
                        mma1688(da[1], f[2], f[3], f[2]); mma1688(db[1], f[2], f[3], f[3]);
                    }
                }
#pragma unroll
                for (int i = 0; i < 4; i++) {
                    const int ch = 7 * j + 2 * i + (lane >> 4);
                    ldsm4(sb + OFF_X + mrow + (ch >> 3) * 16384 + (((ch ^ lane) & 7) << 4), xr + 4 * i);
                }
                mv = ld_relaxed4(msrc);
                warp_arrive(BAR(B_XFREE));
                float qa = (lr & 1) ? da[0][1] + da[1][1] : da[0][0] + da[1][0];
                float qb = (lr & 1) ? db[0][3] + db[1][3] : db[0][2] + db[1][2];
                const int src = (lane & ~3) | (lr >> 1);
                qa = __shfl_sync(~0u, qa, src);
                qb = __shfl_sync(~0u, qb, src);
                ln_coeffs(ds[0] * (1.f / DM), qa * (1.f / DM), ra2, na2);
                ln_coeffs(ds[2] * (1.f / DM), qb * (1.f / DM), rb2, nb2);
#pragma unroll
                for (int i = 0; i < 4 * NPRE; i += 2) { h[i] = hfma2(h[i], ra2, na2); h[i + 1] = hfma2(h[i + 1], rb2, nb2); }
            }
            PROFC(1);
            {
                float ak[28], av[28], aq[28];
                uint32_t kp[14], vp[14];
                const uint64_t bq0 = (DB128 & ~0xFFFFFFFFull) | (mkdesc(sb + OFF_X, DB128) + kh), bk0 = bq0 + (OFF_Y >> 4), bv0 = bk0 + (HALF >> 4);
                uint32_t* kvg = act + RB_KV + j * 7168 + (8 * w + 2 * wi) * 224 + lane;
                mod_store(sb, mv, msrc, mi);
                bar_sync(3, 256);
                if (warp == 0) warp_arrive(BAR(B_MOD1));
                WAIT(B_FULLK, 0);
                PROFC(2);
                reg_def<28>(ak);
#pragma unroll
                for (int g4 = 0; g4 < 4; g4++) {
#pragma unroll
                    for (int ks = 7 * g4; ks < 7 * g4 + 7; ks++) {
                        const uint4 st = *(const uint4*)(smem + M_ST + ks * 64 + q * 16);
                        if (ks >= NPRE) {
                            h[4 * ks] = hfma2(h[4 * ks], ra2, na2); h[4 * ks + 1] = hfma2(h[4 * ks + 1], rb2, nb2);
                            h[4 * ks + 2] = hfma2(h[4 * ks + 2], ra2, na2); h[4 * ks + 3] = hfma2(h[4 * ks + 3], rb2, nb2);
                        }
                        h[4 * ks] = hfma2(h[4 * ks], st.x, st.y); h[4 * ks + 1] = hfma2(h[4 * ks + 1], st.x, st.y);
                        h[4 * ks + 2] = hfma2(h[4 * ks + 2], st.z, st.w); h[4 * ks + 3] = hfma2(h[4 * ks + 3], st.z, st.w);
                    }
                    WG_FENCE();
#pragma unroll
                    for (int ks = 7 * g4; ks < 7 * g4 + 7; ks++) wgmma_rl_56(ak, h[4 * ks], h[4 * ks + 1], h[4 * ks + 2], h[4 * ks + 3], bk0 + ks * 128, ks != 0);
                }
                WG_COMMIT();
                PROFC(3);
                WAIT(B_FULLV, 0);
                reg_def<28>(av);
                WG_FENCE();
#pragma unroll
                for (int ks = 0; ks < 8; ks++) wgmma_rl_56(av, h[4 * ks], h[4 * ks + 1], h[4 * ks + 2], h[4 * ks + 3], bv0 + ks * 128, ks != 0);
                WG_COMMIT();
                WG_WAIT(1);
                reg_fence<28>(ak);
#pragma unroll
                for (int g = 0; g < 7; g++) {
                    kp[2 * g] = pack2(ak[4 * g], ak[4 * g + 1]); kp[2 * g + 1] = pack2(ak[4 * g + 2], ak[4 * g + 3]);
                    kvg[g * 32] = kp[2 * g]; kvg[224 + g * 32] = kp[2 * g + 1];
                }
                warp_arrive(BAR(B_PUB));
                PROFC(4);
                WG_FENCE();
#pragma unroll
                for (int ks = 8; ks < 28; ks++) wgmma_rl_56(av, h[4 * ks], h[4 * ks + 1], h[4 * ks + 2], h[4 * ks + 3], bv0 + ks * 128, 1);
                WG_COMMIT();
                WAIT(B_FULLQ, 0);
                reg_def<28>(aq);
                WG_FENCE();
#pragma unroll
                for (int ks = 0; ks < 8; ks++) wgmma_rl_56(aq, h[4 * ks], h[4 * ks + 1], h[4 * ks + 2], h[4 * ks + 3], bq0 + ks * 128, ks != 0);
                WG_COMMIT();
                WG_WAIT(1);
                reg_fence<28>(av);
#pragma unroll
                for (int g = 0; g < 7; g++) {
                    vp[2 * g] = pack2(av[4 * g], av[4 * g + 1]); vp[2 * g + 1] = pack2(av[4 * g + 2], av[4 * g + 3]);
                    kvg[3584 + g * 32] = vp[2 * g]; kvg[3584 + 224 + g * 32] = vp[2 * g + 1];
                }
                warp_arrive(BAR(B_PUB + 1));
                PROFC(5);
                WG_FENCE();
#pragma unroll
                for (int ks = 8; ks < 28; ks++) wgmma_rl_56(aq, h[4 * ks], h[4 * ks + 1], h[4 * ks + 2], h[4 * ks + 3], bq0 + ks * 128, 1);
                WG_COMMIT();
                WAIT(B_PUB + 1, 0);
                const uint32_t rg = 8 * w + 2 * wi + ((lane >> 3) & 1);
                const uint32_t ko = sb + OFF_Y + Y_KOWN + rg * 896 + (lane & 7) * 16, qo = sb + OFF_Y + Y_Q + rg * 1024 + (lane >> 4) * 128 + (lane & 7) * 16;
#pragma unroll
                for (int g = 0; g < 6; g += 2) {
                    stsm4(ko + (g + (lane >> 4)) * 128, kp[2 * g], kp[2 * g + 1], kp[2 * g + 2], kp[2 * g + 3]);
                    stsm4(ko + (Y_VOWN - Y_KOWN) + (g + (lane >> 4)) * 128, vp[2 * g], vp[2 * g + 1], vp[2 * g + 2], vp[2 * g + 3]);
                }
                stsm4(ko + (lane >> 4) * (Y_VOWN - Y_KOWN) + 6 * 128, kp[12], kp[13], vp[12], vp[13]);
                WG_WAIT(0);
                reg_fence<28>(aq);
                __syncwarp();
                if (lane < 3 && w == 1) mbar_arrive(BAR(B_EMPTY + lane));
                uint32_t qp[14];
#pragma unroll
                for (int i = 0; i < 14; i++) qp[i] = pack2(aq[2 * i], aq[2 * i + 1]);
                stsm4(qo, qp[0], qp[1], qp[2], qp[3]);
                stsm4(qo + 256, qp[4], qp[5], q < 2 ? qp[6] : 0u, q < 2 ? qp[7] : 0u);
                stsm4(qo + 512, q < 2 ? 0u : qp[6], q < 2 ? 0u : qp[7], qp[8], qp[9]);
                stsm4(qo + 768, qp[10], qp[11], qp[12], qp[13]);
                if (!sc) bar_sync(3, 256);
            }
        }
        PROFC(6);
        WAIT(B_KRFULL, 0);
        PROFC(7);
        if (RUN(2)) {
#pragma unroll 1
            for (int hf = sc; hf < 2; hf++) {
                COORDS
                float s[136];
                float na = 0.f, nb = 0.f;
                const float CS = 0.18898223650461361f * 1.4426950408889634f;
                const int kg0 = 8 * hf + 2 * wi;
                const int pmin = 16 - 8 * r - 4 * hf - wi;
                const float NEG = __int_as_float(0xFF800000);
                {
                    uint32_t F[8];
                    const uint32_t qa = sb + OFF_Y + Y_Q + (kg0 + ((lane >> 3) & 1)) * 1024 + (4 * w + (lane >> 4)) * 128 + (lane & 7) * 16;
                    ldsm4(qa, F); ldsm4(qa + 256, F + 4);
                    uint32_t ka = sb + OFF_Y + Y_K + kg0 * 896 + (3 * w + (lane >> 3)) * 128 + (lane & 7) * 16;
#pragma unroll
                    for (int g = 0; g < 34; g++) {
                        uint32_t B[4];
                        if (g >= 12 && g % 4 == 0) ka += __float_as_uint(s[4 * (g - 12)]) & p.zero;
                        ldsm4(ka + g * 896, B);
                        mma16816_first(s + 4 * g, F[0], F[1], F[2], F[3], B[0], B[1]);
                        mma16816_v(s + 4 * g, F[4], F[5], F[6], F[7], B[2], B[3]);
                    }
                    const bool c0 = 2 * q > lr, c1 = 2 * q + 1 > lr;
                    if (!c0) { s[0] = NEG; s[6] = NEG; }
                    if (!c1) { s[1] = NEG; s[7] = NEG; }
                    s[2] = NEG; s[3] = NEG;
                    if (c0) { s[128] = NEG; s[134] = NEG; }
                    if (c1) { s[129] = NEG; s[135] = NEG; }
                    s[132] = NEG; s[133] = NEG;
                    float ma = NEG, mb = NEG;
#pragma unroll
                    for (int pp = 0; pp < 17; pp++) {
                        const float* e = s + 8 * pp;
                        const float bias = pp < pmin ? NEG : 0.f;
                        ma = fmaxf(ma, fmaxf(fmaxf(e[0], e[1]), fmaxf(e[4], e[5])) + bias);
                        mb = fmaxf(mb, fmaxf(fmaxf(e[2], e[3]), fmaxf(e[6], e[7])) + bias);
                    }
                    ma = fmaxf(ma, __shfl_xor_sync(~0u, ma, 1)); mb = fmaxf(mb, __shfl_xor_sync(~0u, mb, 1));
                    ma = fmaxf(ma, __shfl_xor_sync(~0u, ma, 2)); mb = fmaxf(mb, __shfl_xor_sync(~0u, mb, 2));
                    na = -ma * CS; nb = -mb * CS;
                }
                PROFC(8 + 3 * hf);
                {
                    WAIT(B_VRFULL, 0);
                    float o[16] = {}, rs[4] = {};
                    uint32_t pk[2];
                    const uint32_t va = sb + OFF_Y + Y_VR + (kg0 + ((lane >> 3) & 1)) * 896 + (3 * w + (lane >> 4)) * 128 + (lane & 7) * 16;
#pragma unroll
                    for (int pp = 0; pp < 17; pp++) {
                        uint32_t B[8];
                        const uint32_t v = va + pp * 1792 + (pp == 16 || (pp >= 9 && kg0 + 2 * pp >= 32) ? Y_VOWN - 32 * 896 : 0);
                        ldsm4t(v, B); ldsm4t(v + 256, B + 4);
                        float e[8];
                        const float bias = __uint_as_float((pp < pmin ? 0xFF800000u : 0u) | ((pp < 2 ? B[0] : pk[pp & 1]) & p.zero));
#pragma unroll
                        for (int i = 0; i < 8; i++) e[i] = ex2(fmaf(s[8 * pp + i], CS, ((i & 2) ? nb : na) + bias));
                        const uint32_t p0 = pack2(e[0], e[1]), p1 = pack2(e[2], e[3]), p2 = pack2(e[4], e[5]), p3 = pack2(e[6], e[7]);
                        pk[pp & 1] = p3;
                        mma16816(rs, p0, p1, p2, p3, 0x3F803F80u, 0x3F803F80u);
#pragma unroll
                        for (int g = 0; g < 4; g++) mma16816(o + 4 * g, p0, p1, p2, p3, B[2 * g], B[2 * g + 1]);
                    }
                    PROFC(9 + 3 * hf);
                    const float ia = rcp(rs[0]), ib = rcp(rs[2]);
                    uint32_t* og = act + RB_O + hf * 14336 + (7 * j + 3 * w) * 256 + wi * 64 + lane;
#pragma unroll
                    for (int g = 0; g < 4; g++) {
                        if ((g == 3 - 3 * w) ? ((q >> 1) == w) : true) {
                            og[g * 256] = pack2(o[4 * g] * ia, o[4 * g + 1] * ia);
                            og[g * 256 + 32] = pack2(o[4 * g + 2] * ib, o[4 * g + 3] * ib);
                        }
                    }
                    warp_arrive(BAR(B_PUB + 2 + hf));
                    PROFC(10 + 3 * hf);
                }
            }
        }
        uint32_t x1p[14];
        COORDS
        constexpr uint64_t DT = dconst(1024, 128, 0);
        const int tile = opaque((lds1(sb + M_EPOCH) & 1) * 2 + w);
        if (RUN(4)) {
            float ac[28];
            const uint32_t ad = mkdesc(sb + (w ? OFF_Y + HALF : OFF_X), DT), bd = mkdesc(sb + OFF_X + HALF, DB128) + kh;
            WAIT(B_WOFULL, 0);
            WAIT(B_MOD1, 1);
            WAIT(B_GFULL + w, 0);
            PROFC(28);
            reg_def<28>(ac);
#pragma unroll 1
            for (int u = 0; u < 4; u++) {
                if (u == 2) WAIT(B_XFULL + 2 + w, 1);
                WG_FENCE();
#pragma unroll
                for (int i = 0; i < 7; i++) wgmma_ss_56<DT, DB128>(ac, ad + (7 * u + i) * 128, bd + (7 * u + i) * 128, (u | i) != 0);
            }
            WG_COMMIT();
            WG_WAIT(0);
            reg_fence<28>(ac);
            PROFC(14);
            __syncwarp();
            if (lane < 3) mbar_arrive(BAR(B_EMPTY + 4 - w + lane));
            if (lane < 3 && w == 0) mbar_arrive(BAR(B_EMPTY + lane));
            float ds[4] = {}, da[4] = {}, db[4] = {};
            uint32_t* xo = act + RB_X1 + tile * 14336 + 7 * j * 256 + wi * 64 + lane;
#pragma unroll
            for (int g = 0; g < 7; g++) {
                const float2 ga = *(const float2*)(smem + M_G + (8 * g + 2 * q) * 4);
                x1p[2 * g] = pack2(fmaf(ga.x, ac[4 * g], bf_lo(xr[2 * g])), fmaf(ga.y, ac[4 * g + 1], bf_hi(xr[2 * g])));
                x1p[2 * g + 1] = pack2(fmaf(ga.x, ac[4 * g + 2], bf_lo(xr[2 * g + 1])), fmaf(ga.y, ac[4 * g + 3], bf_hi(xr[2 * g + 1])));
                st_relaxed(xo + g * 256, nz(x1p[2 * g])); st_relaxed(xo + g * 256 + 32, nz(x1p[2 * g + 1]));
                mma1688(ds, x1p[2 * g], x1p[2 * g + 1], 0x3F803F80u);
                mma1688(da, x1p[2 * g], x1p[2 * g + 1], x1p[2 * g]);
                mma1688(db, x1p[2 * g], x1p[2 * g + 1], x1p[2 * g + 1]);
            }
            const int src = (lane & ~3) | (lr >> 1);
            const float qa = __shfl_sync(~0u, (lr & 1) ? da[1] : da[0], src), qb = __shfl_sync(~0u, (lr & 1) ? db[3] : db[2], src);
            const float kk = (q & 1) ? ((q & 2) ? qb : qa) : ((q & 2) ? ds[2] : ds[0]);
            st_relaxed(act + RB_ST + ((tile * 8 + j) * 64 + 16 * wi + lr + 4 * (q & 2)) * 2 + (q & 1), nz(__float_as_uint(kk)));
            __syncwarp();
            if (lane < 2) mbar_arrive(BAR(B_PUB + 4 + w));
        } else reg_def<14>(x1p);
        PROFC(15);
        uint32_t h2a[32], h2b[24];
        {
            const int fa = pass_f(fs, 0), fb = pass_f(fs, 1), fc = pass_f(fs, 2);
            uint32_t* h2g = act + RB_H2 + (8 * w + 2 * wi) * 32 + lane;
            const uint32_t a0 = mkdesc(sb + OFF_Y + w * HALF, DT);
            if (RUN(3)) {
                uint32_t ra2, na2, rb2, nb2;
                {
                    const uint32_t* sg = act + RB_ST + ((tile * 8 + 2 * q) * 64 + 16 * wi + lr) * 2;
                    uint2 u[4];
                    WAIT(B_GFULL + 2 + w, 0);
                    PROFC(16);
#pragma unroll
                    for (int i = 0; i < 4; i++) { const float2 v = lds2f(sb + OFF_X + X_STAT + w * 49152 + ((2 * q + (i >> 1)) * 64 + 16 * wi + lr + 8 * (i & 1)) * 8); u[i] = make_uint2(__float_as_uint(v.x), __float_as_uint(v.y)); }
                    while (__any_sync(~0u, min(min(min(u[0].x, u[0].y), min(u[1].x, u[1].y)), min(min(u[2].x, u[2].y), min(u[3].x, u[3].y))) < 1u - sc)) {
#pragma unroll
                        for (int i = 0; i < 4; i++) u[i] = ld_relaxed2(sg + (i >> 1) * 128 + (i & 1) * 16);
                    }
                    warp_arrive(BAR(B_EMPTY + 3 + 3 * w));
                    float v[4] = {__uint_as_float(u[0].x) + __uint_as_float(u[2].x), __uint_as_float(u[0].y) + __uint_as_float(u[2].y),
                                  __uint_as_float(u[1].x) + __uint_as_float(u[3].x), __uint_as_float(u[1].y) + __uint_as_float(u[3].y)};
#pragma unroll
                    for (int i = 0; i < 4; i++) { v[i] += __shfl_xor_sync(~0u, v[i], 1); v[i] += __shfl_xor_sync(~0u, v[i], 2); }
                    ln_coeffs(v[0] * (1.f / DM), v[1] * (1.f / DM), ra2, na2);
                    ln_coeffs(v[2] * (1.f / DM), v[3] * (1.f / DM), rb2, nb2);
                }
                const uint32_t ha = sb + OFF_Y + w * HALF + (lane >> 4) * 1024 + (2 * wi + ((lane >> 3) & 1)) * 128 + (lane & 7) * 16;
                const uint32_t sta = sb + M_ST + q * 16;
                const uint32_t* xg = act + RB_X1 + tile * 14336 + (lane >> 4) * 256 + wi * 64 + (lane & 15) * 4;
                uint32_t x[8];
                const uint32_t xs = sb + OFF_Y + w * HALF + (lane >> 4) * 1024 + wi * 256 + (lane & 15) * 16;
                uint4 st[2];
                auto load = [&](int s) {
                    if (s == 4) mbar_wait_c(BAR(B_XFULL + 4 + w), 1);
                    ldsm4(ha + s * 4096, x); ldsm4(ha + s * 4096 + 2048, x + 4);
                    st[0] = lds4(sta + s * 128); st[1] = lds4(sta + s * 128 + 64);
                };
                auto prep = [&](int s, uint32_t* f) {
                    if (__any_sync(~0u, min(min(min(x[0], x[1]), min(x[2], x[3])), min(min(x[4], x[5]), min(x[6], x[7]))) < 1u - sc)) {
                        WG_WAIT(0);
                        x1_fix(xg, xs, s);
                        ldsm4(ha + s * 4096, x); ldsm4(ha + s * 4096 + 2048, x + 4);
                    }
#pragma unroll
                    for (int i = 0; i < 2; i++) {
                        f[4 * i] = hfma2(hfma2(x[4 * i], ra2, na2), st[i].x, st[i].y); f[4 * i + 1] = hfma2(hfma2(x[4 * i + 1], rb2, nb2), st[i].x, st[i].y);
                        f[4 * i + 2] = hfma2(hfma2(x[4 * i + 2], ra2, na2), st[i].z, st[i].w); f[4 * i + 3] = hfma2(hfma2(x[4 * i + 3], rb2, nb2), st[i].z, st[i].w);
                    }
                    if (s < 13) load(s + 1);
                    stsm4(ha + s * 4096, f[0], f[1], f[2], f[3]); stsm4(ha + s * 4096 + 2048, f[4], f[5], f[6], f[7]);
                };
                float ac[128];
                uint32_t fr[3][8];
                uint64_t bd = (DB128 & ~0xFFFFFFFFull) | mkdesc(sb, DB128);
                reg_def<128>(ac);
                load(0);
                prep(0, fr[0]);
                PROFC(17);
#pragma unroll
                for (int s = 0; s < 14; s++) {
                    const uint32_t* f = fr[s % 3];
                    WAIT(B_FULL + g1_slot(s), s >= 7);
                    WG_FENCE();
                    wgmma_rl_256(ac, f[0], f[1], f[2], f[3], bd, s != 0);
                    wgmma_rl_256(ac, f[4], f[5], f[6], f[7], bd + 128, 1);
                    bd += s == 6 ? p.zero - 6 * 1024ull : 1024;
                    WG_COMMIT();
                    if (s < 13) prep(s + 1, fr[(s + 1) % 3]);
                    if (s > 0) { WG_WAIT(1); warp_arrive(BAR(B_EMPTY + g1_slot(s - 1))); }
                }
                fence_async_smem();
                PROFC(18);
                WG_WAIT(0);
                reg_fence<128>(ac);
                warp_arrive(BAR(B_EMPTY + 6));
#pragma unroll
                for (int g = 0; g < 16; g++) {
                    h2a[2 * g] = hmul2(pack2_relu(ac[4 * g], ac[4 * g + 1]), pack2(ac[64 + 4 * g], ac[64 + 4 * g + 1]));
                    h2a[2 * g + 1] = hmul2(pack2_relu(ac[4 * g + 2], ac[4 * g + 3]), pack2(ac[64 + 4 * g + 2], ac[64 + 4 * g + 3]));
                }
                bar_sync(1 + w, 128);
            } else reg_def<32>(h2a);
            PROFC(19);
            if (RUN(5)) {
                float ac[64];
                reg_def<64>(ac);
                const uint32_t bx = mkdesc(sb, dconst(8192, 1024, 1));
#pragma unroll kB
                for (int s = 0; s < 7; s++) {
                    WAIT(B_FULL + s, 0);
                    const uint32_t ad = a0 + s * 512, bd = bx + (slot_off(s) >> 4);
                    WG_FENCE();
#pragma unroll
                    for (int k = 0; k < 4; k++) wgmma_ss_128<DT, DB128>(ac, ad + k * 128, bd + k * 128, (s | k) != 0);
                    WG_COMMIT();
                    if (s == 1) {
#pragma unroll
                        for (int g = 0; g < 16; g++) { h2g[(fa / 8 + g) * 512] = h2a[2 * g]; h2g[(fa / 8 + g) * 512 + 32] = h2a[2 * g + 1]; }
                        warp_arrive(BAR(B_PUB + 6));
                    }
                    if (s > 0) { WG_WAIT(1); warp_arrive(BAR(B_EMPTY + s - 1)); }
                }
                WG_WAIT(0);
                reg_fence<64>(ac);
                warp_arrive(BAR(B_EMPTY + 6));
#pragma unroll
                for (int g = 0; g < 8; g++) {
                    h2b[2 * g] = hmul2(pack2_relu(ac[4 * g], ac[4 * g + 1]), pack2(ac[32 + 4 * g], ac[32 + 4 * g + 1]));
                    h2b[2 * g + 1] = hmul2(pack2_relu(ac[4 * g + 2], ac[4 * g + 3]), pack2(ac[32 + 4 * g + 2], ac[32 + 4 * g + 3]));
                }
            } else reg_def<16>(h2b);
            PROFC(27);
            if (RUN(6)) {
                float ac[32];
                reg_def<32>(ac);
                const uint32_t bx = mkdesc(sb, dconst(4096, 512, 2));
#pragma unroll kC
                for (int s = 0; s < 7; s++) {
                    WAIT(B_FULL + s, 1);
                    const uint32_t ad = a0 + s * 512, bd = bx + (slot_off(s) >> 4);
                    WG_FENCE();
#pragma unroll
                    for (int k = 0; k < 4; k++) wgmma_ss_64<DT, dconst(4096, 512, 2)>(ac, ad + k * 128, bd + k * 64, (s | k) != 0);
                    WG_COMMIT();
                    if (s == 1) {
#pragma unroll
                        for (int g = 0; g < 8; g++) { h2g[(fb / 8 + g) * 512] = h2b[2 * g]; h2g[(fb / 8 + g) * 512 + 32] = h2b[2 * g + 1]; }
                        warp_arrive(BAR(B_PUB + 7));
                    }
                    if (s > 0) { WG_WAIT(1); warp_arrive(BAR(B_EMPTY + s - 1)); }
                }
                WG_WAIT(0);
                reg_fence<32>(ac);
                __syncwarp();
                if (lane < 6) mbar_arrive(BAR(B_EMPTY + 6 + lane));
                PROFC(20);
#pragma unroll
                for (int g = 0; g < 4; g++) {
                    h2b[16 + 2 * g] = hmul2(pack2_relu(ac[4 * g], ac[4 * g + 1]), pack2(ac[16 + 4 * g], ac[16 + 4 * g + 1]));
                    h2b[16 + 2 * g + 1] = hmul2(pack2_relu(ac[4 * g + 2], ac[4 * g + 3]), pack2(ac[16 + 4 * g + 2], ac[16 + 4 * g + 3]));
                    h2g[(fc / 8 + g) * 512] = h2b[16 + 2 * g]; h2g[(fc / 8 + g) * 512 + 32] = h2b[16 + 2 * g + 1];
                }
                warp_arrive(BAR(B_PUB + 8));
                asm volatile("barrier.cluster.wait.aligned;" ::: "memory");
                if (lane == 0 && !sc) {
                    uint32_t rb;
                    asm volatile("mapa.shared::cluster.u32 %0, %1, %2;" : "=r"(rb) : "r"(BAR(B_PEER)), "r"(kh ^ 1));
                    asm volatile("mbarrier.arrive.relaxed.cluster.shared::cluster.b64 _, [%0];" ::"r"(rb) : "memory");
                }
            } else reg_def<8>(h2b + 16);
        }
        PROFC(21);
        if (RUN(7)) {
            float ac[56];
            reg_def<56>(ac);
            constexpr uint64_t DAN = dconst(2048, 128, 0);
            constexpr uint64_t DW = dconst(128, 512, 0);
            const uint32_t bx = mkdesc(sb, DW);
#pragma unroll
            for (int e = 0; e < 4; e++) {
                WAIT(B_FULL + e, 0);
                const uint64_t bd = ((DW & ~0xFFFFFFFFull) | bx) + (slot_off(e) >> 4);
                const uint32_t* hh = e < 2 ? h2a + 16 * e : h2b + 16 * (e - 2);
                WG_FENCE();
#pragma unroll
                for (int k = 0; k < (e < 3 ? 4 : 2); k++) wgmma_rl_112(ac, hh[4 * k], hh[4 * k + 1], hh[4 * k + 2], hh[4 * k + 3], bd + (k >> 1) * 512 + (k & 1) * 16, (e | k) != 0);
                WG_COMMIT();
                if (e > 0) { WG_WAIT(1); warp_arrive(BAR(B_EMPTY + e - 1)); }
            }
            PROFC(22);
            uint32_t ad = mkdesc(sb + 4 * 16384 + 8192 + w * 1024, DAN), bd = bx + 4 * 1024, fb_ = BAR(B_FULL + 4), eb_ = BAR(B_EMPTY + 3), par = sc;
#pragma unroll 1
            for (int e = 4; e < 25; e++) {
                mbar_wait_c(fb_, par);
                WG_FENCE();
                wgmma_ss_112<DAN, DW>(ac, ad, bd, 1);
                wgmma_ss_112<DAN, DW>(ac, ad + 256, bd + 16, 1);
                WG_COMMIT();
                WG_WAIT(1);
                warp_arrive(eb_);
                eb_ = fb_ + 8 * (B_EMPTY - B_FULL);
                ad += 1024; bd += 1024; fb_ += 8;
                if (e == 11 || e == 23) { ad -= 12 * 1024; bd -= 12 * 1024; fb_ -= 96; par = (par ^ 1) | sc; }
            }
            mbar_wait_cluster(BAR(B_PEER), sc);
            WG_WAIT(0);
            reg_fence<56>(ac);
            PROFC(24);
            uint32_t rdst, rbar;
            asm volatile("mapa.shared::cluster.u32 %0, %1, %2;" : "=r"(rdst) : "r"(sb + OFF_Y + (5 + w) * 16384 + t * 16), "r"(kh ^ 1 ^ sc));
            asm volatile("mapa.shared::cluster.u32 %0, %1, %2;" : "=r"(rbar) : "r"(BAR(B_XCH + w)), "r"(kh ^ 1 ^ sc));
#pragma unroll
            for (int g = 0; g < 7; g++) {
                const float v0 = ac[28 + 4 * g + 0], v1 = ac[28 + 4 * g + 1];
                const float v2 = ac[28 + 4 * g + 2], v3 = ac[28 + 4 * g + 3];
                if (!sc) asm volatile("st.async.shared::cluster.mbarrier::complete_tx::bytes.v4.f32 [%0], {%1,%2,%3,%4}, [%5];"
                             ::"r"(rdst + g * 2048), "f"(v0), "f"(v1), "f"(v2), "f"(v3), "r"(rbar) : "memory");
            }
            mbar_wait_cluster(BAR(B_XCH + w), sc);
            PROFC(25);
            bf16* og = (sc ? (bf16*)act : p.out + (size_t)128 * r * DM) + (size_t)ra * DM + 56 * j + 2 * q;
#pragma unroll
            for (int g = 0; g < 7; g++) {
                const uint4 rv = *(const uint4*)(smem + OFF_Y + (5 + w) * 16384 + t * 16 + g * 2048);
                const float2 gb = *(const float2*)(smem + M_G + 224 + (8 * g + 2 * q) * 4);
                const float v0 = ac[4 * g + 0] + __uint_as_float(rv.x), v1 = ac[4 * g + 1] + __uint_as_float(rv.y);
                const float v2 = ac[4 * g + 2] + __uint_as_float(rv.z), v3 = ac[4 * g + 3] + __uint_as_float(rv.w);
                *(uint32_t*)(og + 8 * g) = pack2(fmaf(gb.x, v0, bf_lo(x1p[2 * g])), fmaf(gb.y, v1, bf_hi(x1p[2 * g])));
                *(uint32_t*)(og + 8 * DM + 8 * g) = pack2(fmaf(gb.x, v2, bf_lo(x1p[2 * g + 1])), fmaf(gb.y, v3, bf_hi(x1p[2 * g + 1])));
            }
        }
        PROFC(26);
        bar_sync(1 + w, 128);
        if (wi == 0) warp_arrive(BAR(B_DONE));
        return;
    }
    helper_late(p, r, j, warp PROF_ARGS);
}

#undef act
typedef CUresult (*EncodeFn)(CUtensorMap*, CUtensorMapDataType, cuuint32_t, void*, const cuuint64_t*, const cuuint64_t*, const cuuint32_t*,
                             const cuuint32_t*, CUtensorMapInterleave, CUtensorMapSwizzle, CUtensorMapL2promotion, CUtensorMapFloatOOBfill);

static void make_map(EncodeFn fn, CUtensorMap* m, const void* ptr, uint64_t d0, uint64_t d1, uint64_t d2, uint64_t s1, uint64_t s2,
                     uint32_t b0, uint32_t b1, uint32_t b2, CUtensorMapSwizzle sw) {
    cuuint64_t dims[3] = {d0, d1, d2}, strides[2] = {s1, s2};
    cuuint32_t box[3] = {b0, b1, b2}, es[3] = {1, 1, 1};
    CUresult rc = fn(m, CU_TENSOR_MAP_DATA_TYPE_BFLOAT16, 3, (void*)ptr, dims, strides, box, es, CU_TENSOR_MAP_INTERLEAVE_NONE, sw,
                     CU_TENSOR_MAP_L2_PROMOTION_L2_128B, CU_TENSOR_MAP_FLOAT_OOB_FILL_NONE);
    (void)rc;
}

extern "C" void kernel_launch(void* const* d_in, const int* in_sizes, int n_in, void* d_out, int out_size) {
    (void)in_sizes; (void)n_in; (void)out_size;
    static EncodeFn fn = nullptr;
    static uint32_t* act_base = nullptr;
    if (!fn) {
        cudaDriverEntryPointQueryResult st;
        cudaGetDriverEntryPoint("cuTensorMapEncodeTiled", (void**)&fn, cudaEnableDefault, &st);
        void* a = nullptr;
        cudaGetSymbolAddress(&a, g_act);
        act_base = (uint32_t*)(((uintptr_t)a + 0xFFFFF) & ~(uintptr_t)0xFFFFF);
        cudaFuncSetAttribute(fused_block_kernel, cudaFuncAttributeMaxDynamicSharedMemorySize, SMEM_BYTES);
    }
    Params p;
    p.x = (const bf16*)d_in[0];
    const bf16* wqkv = (const bf16*)d_in[1];
    p.wqkv = wqkv;
    p.wop = (const bf16*)d_in[2];
    p.wg = (const bf16*)d_in[4];
    p.wu = (const bf16*)d_in[5];
    p.wd = (const bf16*)d_in[6];
    p.c = (const bf16*)d_in[7];
    p.wmod = (const bf16*)d_in[8];
    p.out = (bf16*)d_out;
    p.zero = 0;
    p.actb = act_base;
    make_map(fn, &p.wm, p.wmod, 2688, 448, 1, 5376, 5376 * 448, 16, 224, 1, CU_TENSOR_MAP_SWIZZLE_NONE);
    make_map(fn, &p.xm, p.x, 448, 2048, 1, 896, 896 * 2048, 64, 128, 1, CU_TENSOR_MAP_SWIZZLE_128B);
    make_map(fn, &p.qkv, wqkv, 1344, 448, 1, 2688, 2688 * 448, 64, 224, 1, CU_TENSOR_MAP_SWIZZLE_128B);
    make_map(fn, &p.wo, p.wop, 448, 448, 1, 896, 896 * 448, 64, 224, 1, CU_TENSOR_MAP_SWIZZLE_128B);
    make_map(fn, &p.ga, p.wg, 64, 448, 28, 3584, 128, 64, 32, 2, CU_TENSOR_MAP_SWIZZLE_128B);
    make_map(fn, &p.ua, p.wu, 64, 448, 28, 3584, 128, 64, 32, 2, CU_TENSOR_MAP_SWIZZLE_128B);
    make_map(fn, &p.gb, p.wg, 64, 448, 28, 3584, 128, 64, 64, 1, CU_TENSOR_MAP_SWIZZLE_128B);
    make_map(fn, &p.ub, p.wu, 64, 448, 28, 3584, 128, 64, 64, 1, CU_TENSOR_MAP_SWIZZLE_128B);
    make_map(fn, &p.gc, p.wg, 32, 448, 56, 3584, 64, 32, 64, 1, CU_TENSOR_MAP_SWIZZLE_64B);
    make_map(fn, &p.uc, p.wu, 32, 448, 56, 3584, 64, 32, 64, 1, CU_TENSOR_MAP_SWIZZLE_64B);
    make_map(fn, &p.dn, p.wd, 8, 1792, 56, 896, 16, 8, 32, 7, CU_TENSOR_MAP_SWIZZLE_NONE);
    fused_block_kernel<<<GRID, 384, SMEM_BYTES>>>(p);
}
```

```cpp
#include <cuda_runtime.h>
#include <cuda_bf16.h>
#include <cuda.h>
#include <stdint.h>

typedef __nv_bfloat16 bf16;

__device__ __forceinline__ void wgmma_rl_56(float* d, uint32_t a0, uint32_t a1, uint32_t a2, uint32_t a3, uint64_t db, int sd) {
  asm volatile("{\n.reg .pred p;\nsetp.ne.b32 p, %33, 0;\n"
    "wgmma.mma_async.sync.aligned.m64n56k16.f32.bf16.bf16 {%0,%1,%2,%3,%4,%5,%6,%7,%8,%9,%10,%11,%12,%13,%14,%15,%16,%17,%18,%19,%20,%21,%22,%23,%24,%25,%26,%27}, {%28,%29,%30,%31}, %32, p, 1, 1, 1;\n}\n"
    : "+f"(d[0]),"+f"(d[1]),"+f"(d[2]),"+f"(d[3]),"+f"(d[4]),"+f"(d[5]),"+f"(d[6]),"+f"(d[7]),"+f"(d[8]),"+f"(d[9]),"+f"(d[10]),"+f"(d[11]),"+f"(d[12]),"+f"(d[13]),"+f"(d[14]),"+f"(d[15]),"+f"(d[16]),"+f"(d[17]),"+f"(d[18]),"+f"(d[19]),"+f"(d[20]),"+f"(d[21]),"+f"(d[22]),"+f"(d[23]),"+f"(d[24]),"+f"(d[25]),"+f"(d[26]),"+f"(d[27])
    : "r"(a0), "r"(a1), "r"(a2), "r"(a3), "l"(db), "r"(sd));
}
template<uint64_t CA, uint64_t CB> __device__ __forceinline__ void wgmma_ss_56(float* d, uint32_t da, uint32_t db, int sd) {
  asm volatile("{\n.reg .pred p;\n.reg .b64 a, b;\nsetp.ne.b32 p, %30, 0;\nmov.b64 a, {%28, %31};\nmov.b64 b, {%29, %32};\n"
    "wgmma.mma_async.sync.aligned.m64n56k16.f32.bf16.bf16 {%0,%1,%2,%3,%4,%5,%6,%7,%8,%9,%10,%11,%12,%13,%14,%15,%16,%17,%18,%19,%20,%21,%22,%23,%24,%25,%26,%27}, a, b, p, 1, 1, 0, 1;\n}\n"
    : "+f"(d[0]),"+f"(d[1]),"+f"(d[2]),"+f"(d[3]),"+f"(d[4]),"+f"(d[5]),"+f"(d[6]),"+f"(d[7]),"+f"(d[8]),"+f"(d[9]),"+f"(d[10]),"+f"(d[11]),"+f"(d[12]),"+f"(d[13]),"+f"(d[14]),"+f"(d[15]),"+f"(d[16]),"+f"(d[17]),"+f"(d[18]),"+f"(d[19]),"+f"(d[20]),"+f"(d[21]),"+f"(d[22]),"+f"(d[23]),"+f"(d[24]),"+f"(d[25]),"+f"(d[26]),"+f"(d[27])
    : "r"(da), "r"(db), "r"(sd), "n"((uint32_t)(CA >> 32)), "n"((uint32_t)(CB >> 32)));
}
__device__ __forceinline__ void wgmma_rl_256(float* d, uint32_t a0, uint32_t a1, uint32_t a2, uint32_t a3, uint64_t db, int sd) {
  asm volatile("{\n.reg .pred p;\nsetp.ne.b32 p, %133, 0;\n"
    "wgmma.mma_async.sync.aligned.m64n256k16.f32.bf16.bf16 {%0,%1,%2,%3,%4,%5,%6,%7,%8,%9,%10,%11,%12,%13,%14,%15,%16,%17,%18,%19,%20,%21,%22,%23,%24,%25,%26,%27,%28,%29,%30,%31,%32,%33,%34,%35,%36,%37,%38,%39,%40,%41,%42,%43,%44,%45,%46,%47,%48,%49,%50,%51,%52,%53,%54,%55,%56,%57,%58,%59,%60,%61,%62,%63,%64,%65,%66,%67,%68,%69,%70,%71,%72,%73,%74,%75,%76,%77,%78,%79,%80,%81,%82,%83,%84,%85,%86,%87,%88,%89,%90,%91,%92,%93,%94,%95,%96,%97,%98,%99,%100,%101,%102,%103,%104,%105,%106,%107,%108,%109,%110,%111,%112,%113,%114,%115,%116,%117,%118,%119,%120,%121,%122,%123,%124,%125,%126,%127}, {%128,%129,%130,%131}, %132, p, 1, 1, 1;\n}\n"
    : "+f"(d[0]),"+f"(d[1]),"+f"(d[2]),"+f"(d[3]),"+f"(d[4]),"+f"(d[5]),"+f"(d[6]),"+f"(d[7]),"+f"(d[8]),"+f"(d[9]),"+f"(d[10]),"+f"(d[11]),"+f"(d[12]),"+f"(d[13]),"+f"(d[14]),"+f"(d[15]),"+f"(d[16]),"+f"(d[17]),"+f"(d[18]),"+f"(d[19]),"+f"(d[20]),"+f"(d[21]),"+f"(d[22]),"+f"(d[23]),"+f"(d[24]),"+f"(d[25]),"+f"(d[26]),"+f"(d[27]),"+f"(d[28]),"+f"(d[29]),"+f"(d[30]),"+f"(d[31]),"+f"(d[32]),"+f"(d[33]),"+f"(d[34]),"+f"(d[35]),"+f"(d[36]),"+f"(d[37]),"+f"(d[38]),"+f"(d[39]),"+f"(d[40]),"+f"(d[41]),"+f"(d[42]),"+f"(d[43]),"+f"(d[44]),"+f"(d[45]),"+f"(d[46]),"+f"(d[47]),"+f"(d[48]),"+f"(d[49]),"+f"(d[50]),"+f"(d[51]),"+f"(d[52]),"+f"(d[53]),"+f"(d[54]),"+f"(d[55]),"+f"(d[56]),"+f"(d[57]),"+f"(d[58]),"+f"(d[59]),"+f"(d[60]),"+f"(d[61]),"+f"(d[62]),"+f"(d[63]),"+f"(d[64]),"+f"(d[65]),"+f"(d[66]),"+f"(d[67]),"+f"(d[68]),"+f"(d[69]),"+f"(d[70]),"+f"(d[71]),"+f"(d[72]),"+f"(d[73]),"+f"(d[74]),"+f"(d[75]),"+f"(d[76]),"+f"(d[77]),"+f"(d[78]),"+f"(d[79]),"+f"(d[80]),"+f"(d[81]),"+f"(d[82]),"+f"(d[83]),"+f"(d[84]),"+f"(d[85]),"+f"(d[86]),"+f"(d[87]),"+f"(d[88]),"+f"(d[89]),"+f"(d[90]),"+f"(d[91]),"+f"(d[92]),"+f"(d[93]),"+f"(d[94]),"+f"(d[95]),"+f"(d[96]),"+f"(d[97]),"+f"(d[98]),"+f"(d[99]),"+f"(d[100]),"+f"(d[101]),"+f"(d[102]),"+f"(d[103]),"+f"(d[104]),"+f"(d[105]),"+f"(d[106]),"+f"(d[107]),"+f"(d[108]),"+f"(d[109]),"+f"(d[110]),"+f"(d[111]),"+f"(d[112]),"+f"(d[113]),"+f"(d[114]),"+f"(d[115]),"+f"(d[116]),"+f"(d[117]),"+f"(d[118]),"+f"(d[119]),"+f"(d[120]),"+f"(d[121]),"+f"(d[122]),"+f"(d[123]),"+f"(d[124]),"+f"(d[125]),"+f"(d[126]),"+f"(d[127])
    : "r"(a0), "r"(a1), "r"(a2), "r"(a3), "l"(db), "r"(sd));
}
template<uint64_t CA, uint64_t CB> __device__ __forceinline__ void wgmma_ss_128(float* d, uint32_t da, uint32_t db, int sd) {
  asm volatile("{\n.reg .pred p;\n.reg .b64 a, b;\nsetp.ne.b32 p, %66, 0;\nmov.b64 a, {%64, %67};\nmov.b64 b, {%65, %68};\n"
    "wgmma.mma_async.sync.aligned.m64n128k16.f32.bf16.bf16 {%0,%1,%2,%3,%4,%5,%6,%7,%8,%9,%10,%11,%12,%13,%14,%15,%16,%17,%18,%19,%20,%21,%22,%23,%24,%25,%26,%27,%28,%29,%30,%31,%32,%33,%34,%35,%36,%37,%38,%39,%40,%41,%42,%43,%44,%45,%46,%47,%48,%49,%50,%51,%52,%53,%54,%55,%56,%57,%58,%59,%60,%61,%62,%63}, a, b, p, 1, 1, 0, 1;\n}\n"
    : "+f"(d[0]),"+f"(d[1]),"+f"(d[2]),"+f"(d[3]),"+f"(d[4]),"+f"(d[5]),"+f"(d[6]),"+f"(d[7]),"+f"(d[8]),"+f"(d[9]),"+f"(d[10]),"+f"(d[11]),"+f"(d[12]),"+f"(d[13]),"+f"(d[14]),"+f"(d[15]),"+f"(d[16]),"+f"(d[17]),"+f"(d[18]),"+f"(d[19]),"+f"(d[20]),"+f"(d[21]),"+f"(d[22]),"+f"(d[23]),"+f"(d[24]),"+f"(d[25]),"+f"(d[26]),"+f"(d[27]),"+f"(d[28]),"+f"(d[29]),"+f"(d[30]),"+f"(d[31]),"+f"(d[32]),"+f"(d[33]),"+f"(d[34]),"+f"(d[35]),"+f"(d[36]),"+f"(d[37]),"+f"(d[38]),"+f"(d[39]),"+f"(d[40]),"+f"(d[41]),"+f"(d[42]),"+f"(d[43]),"+f"(d[44]),"+f"(d[45]),"+f"(d[46]),"+f"(d[47]),"+f"(d[48]),"+f"(d[49]),"+f"(d[50]),"+f"(d[51]),"+f"(d[52]),"+f"(d[53]),"+f"(d[54]),"+f"(d[55]),"+f"(d[56]),"+f"(d[57]),"+f"(d[58]),"+f"(d[59]),"+f"(d[60]),"+f"(d[61]),"+f"(d[62]),"+f"(d[63])
    : "r"(da), "r"(db), "r"(sd), "n"((uint32_t)(CA >> 32)), "n"((uint32_t)(CB >> 32)));
}
template<uint64_t CA, uint64_t CB> __device__ __forceinline__ void wgmma_ss_64(float* d, uint32_t da, uint32_t db, int sd) {
  asm volatile("{\n.reg .pred p;\n.reg .b64 a, b;\nsetp.ne.b32 p, %34, 0;\nmov.b64 a, {%32, %35};\nmov.b64 b, {%33, %36};\n"
    "wgmma.mma_async.sync.aligned.m64n64k16.f32.bf16.bf16 {%0,%1,%2,%3,%4,%5,%6,%7,%8,%9,%10,%11,%12,%13,%14,%15,%16,%17,%18,%19,%20,%21,%22,%23,%24,%25,%26,%27,%28,%29,%30,%31}, a, b, p, 1, 1, 0, 1;\n}\n"
    : "+f"(d[0]),"+f"(d[1]),"+f"(d[2]),"+f"(d[3]),"+f"(d[4]),"+f"(d[5]),"+f"(d[6]),"+f"(d[7]),"+f"(d[8]),"+f"(d[9]),"+f"(d[10]),"+f"(d[11]),"+f"(d[12]),"+f"(d[13]),"+f"(d[14]),"+f"(d[15]),"+f"(d[16]),"+f"(d[17]),"+f"(d[18]),"+f"(d[19]),"+f"(d[20]),"+f"(d[21]),"+f"(d[22]),"+f"(d[23]),"+f"(d[24]),"+f"(d[25]),"+f"(d[26]),"+f"(d[27]),"+f"(d[28]),"+f"(d[29]),"+f"(d[30]),"+f"(d[31])
    : "r"(da), "r"(db), "r"(sd), "n"((uint32_t)(CA >> 32)), "n"((uint32_t)(CB >> 32)));
}
template<uint64_t CA, uint64_t CB> __device__ __forceinline__ void wgmma_ss_112(float* d, uint32_t da, uint32_t db, int sd) {
  asm volatile("{\n.reg .pred p;\n.reg .b64 a, b;\nsetp.ne.b32 p, %58, 0;\nmov.b64 a, {%56, %59};\nmov.b64 b, {%57, %60};\n"
    "wgmma.mma_async.sync.aligned.m64n112k16.f32.bf16.bf16 {%0,%1,%2,%3,%4,%5,%6,%7,%8,%9,%10,%11,%12,%13,%14,%15,%16,%17,%18,%19,%20,%21,%22,%23,%24,%25,%26,%27,%28,%29,%30,%31,%32,%33,%34,%35,%36,%37,%38,%39,%40,%41,%42,%43,%44,%45,%46,%47,%48,%49,%50,%51,%52,%53,%54,%55}, a, b, p, 1, 1, 0, 1;\n}\n"
    : "+f"(d[0]),"+f"(d[1]),"+f"(d[2]),"+f"(d[3]),"+f"(d[4]),"+f"(d[5]),"+f"(d[6]),"+f"(d[7]),"+f"(d[8]),"+f"(d[9]),"+f"(d[10]),"+f"(d[11]),"+f"(d[12]),"+f"(d[13]),"+f"(d[14]),"+f"(d[15]),"+f"(d[16]),"+f"(d[17]),"+f"(d[18]),"+f"(d[19]),"+f"(d[20]),"+f"(d[21]),"+f"(d[22]),"+f"(d[23]),"+f"(d[24]),"+f"(d[25]),"+f"(d[26]),"+f"(d[27]),"+f"(d[28]),"+f"(d[29]),"+f"(d[30]),"+f"(d[31]),"+f"(d[32]),"+f"(d[33]),"+f"(d[34]),"+f"(d[35]),"+f"(d[36]),"+f"(d[37]),"+f"(d[38]),"+f"(d[39]),"+f"(d[40]),"+f"(d[41]),"+f"(d[42]),"+f"(d[43]),"+f"(d[44]),"+f"(d[45]),"+f"(d[46]),"+f"(d[47]),"+f"(d[48]),"+f"(d[49]),"+f"(d[50]),"+f"(d[51]),"+f"(d[52]),"+f"(d[53]),"+f"(d[54]),"+f"(d[55])
    : "r"(da), "r"(db), "r"(sd), "n"((uint32_t)(CA >> 32)), "n"((uint32_t)(CB >> 32)));
}
__device__ __forceinline__ void wgmma_rl_112(float* d, uint32_t a0, uint32_t a1, uint32_t a2, uint32_t a3, uint64_t db, int sd) {
  asm volatile("{\n.reg .pred p;\nsetp.ne.b32 p, %61, 0;\n"
    "wgmma.mma_async.sync.aligned.m64n112k16.f32.bf16.bf16 {%0,%1,%2,%3,%4,%5,%6,%7,%8,%9,%10,%11,%12,%13,%14,%15,%16,%17,%18,%19,%20,%21,%22,%23,%24,%25,%26,%27,%28,%29,%30,%31,%32,%33,%34,%35,%36,%37,%38,%39,%40,%41,%42,%43,%44,%45,%46,%47,%48,%49,%50,%51,%52,%53,%54,%55}, {%56,%57,%58,%59}, %60, p, 1, 1, 1;\n}\n"
    : "+f"(d[0]),"+f"(d[1]),"+f"(d[2]),"+f"(d[3]),"+f"(d[4]),"+f"(d[5]),"+f"(d[6]),"+f"(d[7]),"+f"(d[8]),"+f"(d[9]),"+f"(d[10]),"+f"(d[11]),"+f"(d[12]),"+f"(d[13]),"+f"(d[14]),"+f"(d[15]),"+f"(d[16]),"+f"(d[17]),"+f"(d[18]),"+f"(d[19]),"+f"(d[20]),"+f"(d[21]),"+f"(d[22]),"+f"(d[23]),"+f"(d[24]),"+f"(d[25]),"+f"(d[26]),"+f"(d[27]),"+f"(d[28]),"+f"(d[29]),"+f"(d[30]),"+f"(d[31]),"+f"(d[32]),"+f"(d[33]),"+f"(d[34]),"+f"(d[35]),"+f"(d[36]),"+f"(d[37]),"+f"(d[38]),"+f"(d[39]),"+f"(d[40]),"+f"(d[41]),"+f"(d[42]),"+f"(d[43]),"+f"(d[44]),"+f"(d[45]),"+f"(d[46]),"+f"(d[47]),"+f"(d[48]),"+f"(d[49]),"+f"(d[50]),"+f"(d[51]),"+f"(d[52]),"+f"(d[53]),"+f"(d[54]),"+f"(d[55])
    : "r"(a0), "r"(a1), "r"(a2), "r"(a3), "l"(db), "r"(sd));
}

constexpr int DM = 448;
constexpr int NCTA = 128;
#define MAPPING 1
#define GRID 128
#define PINGPONG 0
#define WIN 6
#define WIN_END 25
#define UNR_B 1
#define UNR_C 1
constexpr int kB = UNR_B, kC = UNR_C;
#define LIKELY(x) __builtin_expect(!!(x), 1)
#define PACE 1
#define PACE_END 6
#define GEMV_AT 1
#define NPRE 14
#define MAP_S 4
constexpr int SPIN_LIMIT = 1 << 22;

constexpr uint32_t OFF_X = 0, OFF_Y = 114688, OFF_MISC = 229376, SMEM_BYTES = 232448;
constexpr uint32_t Y_VR = 0, Y_K = 28672, Y_KOWN = 57344, Y_VOWN = 71680, Y_Q = 86016;
constexpr uint32_t HALF = 57344;
constexpr uint32_t X_STAT = 49152;
constexpr uint32_t M_BAR = OFF_MISC;
constexpr uint32_t M_ST = OFF_MISC + 512;
constexpr uint32_t M_G = OFF_MISC + 2304;
constexpr uint32_t M_EPOCH = OFF_MISC + 3040;
enum { B_XFULL = 0, B_FULLK = 7, B_FULLV = 8, B_FULLQ, B_KRFULL, B_VRFULL, B_WOFULL, B_XCH, B_MOD1 = 15, B_FULL = 16, B_WMFULL = 30,
       B_EMPTY = 32, B_XFREE = B_EMPTY + 12, B_GEMV, B_PEER,
       B_PUB = 47,
       B_WMFREE = 56, B_HRDY, B_GFULL = B_HRDY + 3, B_DONE = 31, B_DUMMY = B_GEMV };

__device__ uint32_t g_ticket;
__device__ __align__(128) uint32_t g_mod[8 * 6 * DM];
__device__ __align__(128) uint32_t g_flag[144 * 128];
constexpr int RB_WORDS = 294912, RB_KV = 0, RB_O = 57344, RB_X1 = 86016, RB_H2 = 143360, RB_ST = 258048, RB_HC = 262144;
__device__ __align__(128) uint32_t g_act[17 * RB_WORDS];
__device__ __align__(128) uint32_t g_wd[56 * 4 * 1792];
#define PROFH(id)
#define PROFH1(id)
#define PROFC(id)

struct alignas(64) Params {
    CUtensorMap wm, xm, qkv, wo, ga, ua, gb, ub, gc, uc, dn;
    const bf16 *x, *c, *wqkv, *wmod, *wg, *wu, *wd, *wop;
    bf16* out;
    uint32_t* actb;
    uint32_t zero;
};

__device__ __forceinline__ void mbar_init(uint32_t bar, int cnt) { asm volatile("mbarrier.init.shared::cta.b64 [%0], %1;" ::"r"(bar), "r"(cnt) : "memory"); }
__device__ __forceinline__ void mbar_expect_tx(uint32_t bar, uint32_t bytes) { asm volatile("mbarrier.arrive.expect_tx.shared::cta.b64 _, [%0], %1;" ::"r"(bar), "r"(bytes) : "memory"); }
__device__ __forceinline__ void mbar_arrive(uint32_t bar) { asm volatile("mbarrier.arrive.shared::cta.b64 _, [%0];" ::"r"(bar) : "memory"); }
__device__ __forceinline__ void mbar_wait(uint32_t bar, uint32_t parity) {
    uint32_t ok; int n = 0;
    do {
        asm volatile("{\n.reg .pred p;\nmbarrier.try_wait.parity.shared::cta.b64 p, [%1], %2;\nselp.u32 %0, 1, 0, p;\n}" : "=r"(ok) : "r"(bar), "r"(parity) : "memory");
        if (++n > SPIN_LIMIT) __trap();
    } while (!ok);
}
__device__ __forceinline__ void mbar_wait_c(uint32_t bar, uint32_t parity) {
    asm volatile("{\n.reg .pred p;\nWL:\nmbarrier.try_wait.parity.shared::cta.b64 p, [%0], %1, 0x989680;\n@!p bra WL;\n}" ::"r"(bar), "r"(parity) : "memory");
}
__device__ __forceinline__ void mbar_wait_cluster(uint32_t bar, uint32_t parity) {
    asm volatile("{\n.reg .pred p;\nWL:\nmbarrier.try_wait.parity.acquire.cluster.shared::cta.b64 p, [%0], %1, 0x989680;\n@!p bra WL;\n}" ::"r"(bar), "r"(parity) : "memory");
}
__device__ __forceinline__ void warp_arrive(uint32_t bar) {
    __syncwarp();
    asm volatile("{\n.reg .pred p;\nelect.sync _|p, 0xffffffff;\n@p mbarrier.arrive.shared::cta.b64 _, [%0];\n}" ::"r"(bar) : "memory");
}
__device__ __forceinline__ int opaque(int v) { return __shfl_sync(~0u, v, 0); }
__device__ __forceinline__ int fresh_tid() { int v; asm volatile("mov.u32 %0, %%tid.x;" : "=r"(v)); return v; }
__device__ __forceinline__ void bar_sync(int id, int n) { asm volatile("bar.sync %0, %1;" ::"r"(id), "r"(n) : "memory"); }
__device__ __forceinline__ void bar_arrive(int id, int n) { asm volatile("bar.arrive %0, %1;" ::"r"(id), "r"(n) : "memory"); }
__device__ __forceinline__ void fence_async_smem() { asm volatile("fence.proxy.async.shared::cta;" ::: "memory"); }
__device__ __forceinline__ void fence_async_global() { asm volatile("fence.proxy.async.global;" ::: "memory"); }
__device__ __forceinline__ void fence_gpu() { asm volatile("fence.release.gpu;" ::: "memory"); }
__device__ __forceinline__ void tma3(uint32_t dst, const CUtensorMap* m, int c0, int c1, int c2, uint32_t bar) {
    asm volatile("cp.async.bulk.tensor.3d.shared::cluster.global.mbarrier::complete_tx::bytes [%0], [%1, {%3, %4, %5}], [%2];"
                 ::"r"(dst), "l"(m), "r"(bar), "r"(c0), "r"(c1), "r"(c2) : "memory");
}
__device__ __forceinline__ void bulk_load(uint32_t dst, const void* src, uint32_t bytes, uint32_t bar) {
    asm volatile("cp.async.bulk.shared::cluster.global.mbarrier::complete_tx::bytes [%0], [%1], %2, [%3];" ::"r"(dst), "l"(src), "r"(bytes), "r"(bar) : "memory");
}
__device__ __forceinline__ void expect_e(uint32_t bar, uint32_t bytes) {
    asm volatile("{\n.reg .pred p;\nelect.sync _|p, 0xffffffff;\n@p mbarrier.arrive.expect_tx.shared::cta.b64 _, [%0], %1;\n}" ::"r"(bar), "r"(bytes) : "memory");
}
__device__ __forceinline__ void tma3_e(uint32_t dst, const CUtensorMap* m, int c0, int c1, int c2, uint32_t bar) {
    asm volatile("{\n.reg .pred p;\nelect.sync _|p, 0xffffffff;\n@p cp.async.bulk.tensor.3d.shared::cluster.global.mbarrier::complete_tx::bytes [%0], [%1, {%3, %4, %5}], [%2];\n}"
                 ::"r"(dst), "l"(m), "r"(bar), "r"(c0), "r"(c1), "r"(c2) : "memory");
}
__device__ __forceinline__ void bulk_e(uint32_t dst, const void* src, uint32_t bytes, uint32_t bar) {
    asm volatile("{\n.reg .pred p;\nelect.sync _|p, 0xffffffff;\n@p cp.async.bulk.shared::cluster.global.mbarrier::complete_tx::bytes [%0], [%1], %2, [%3];\n}"
                 ::"r"(dst), "l"(src), "r"(bytes), "r"(bar) : "memory");
}
__device__ __forceinline__ void init_e(uint32_t bar, int cnt) {
    asm volatile("{\n.reg .pred p;\nelect.sync _|p, 0xffffffff;\n@p mbarrier.init.shared::cta.b64 [%0], %1;\n}" ::"r"(bar), "r"(cnt) : "memory");
}
__device__ __forceinline__ void l2_prefetch_e(const void* src, uint32_t bytes) {
    asm volatile("{\n.reg .pred p;\nelect.sync _|p, 0xffffffff;\n@p cp.async.bulk.prefetch.L2.global [%0], %1;\n}" ::"l"(src), "r"(bytes) : "memory");
}
__device__ __forceinline__ uint32_t ld_relaxed(const uint32_t* p) { uint32_t v; asm volatile("ld.relaxed.gpu.global.u32 %0, [%1];" : "=r"(v) : "l"(p) : "memory"); return v; }
__device__ __forceinline__ void st_relaxed(uint32_t* p, uint32_t v) { asm volatile("st.relaxed.gpu.global.u32 [%0], %1;" ::"l"(p), "r"(v) : "memory"); }
__device__ __forceinline__ uint4 ld_relaxed4(const uint4* p) { uint4 v; asm volatile("ld.relaxed.gpu.global.v4.u32 {%0,%1,%2,%3}, [%4];" : "=r"(v.x), "=r"(v.y), "=r"(v.z), "=r"(v.w) : "l"(p) : "memory"); return v; }
__device__ __forceinline__ void st_relaxed4(uint4* p, uint4 v) { asm volatile("st.relaxed.gpu.global.v4.u32 [%0], {%1,%2,%3,%4};" ::"l"(p), "r"(v.x), "r"(v.y), "r"(v.z), "r"(v.w) : "memory"); }
__device__ __forceinline__ uint4 ldg_nc4(const void* p) { uint4 v; asm volatile("ld.global.nc.L1::no_allocate.v4.u32 {%0,%1,%2,%3}, [%4];" : "=r"(v.x), "=r"(v.y), "=r"(v.z), "=r"(v.w) : "l"(p)); return v; }
__device__ __forceinline__ uint32_t ldg_nc(const void* p) { uint32_t v; asm volatile("ld.global.nc.u32 %0, [%1];" : "=r"(v) : "l"(p)); return v; }
__device__ __forceinline__ uint32_t ld_acquire(const uint32_t* p) { uint32_t v; asm volatile("ld.acquire.gpu.global.u32 %0, [%1];" : "=r"(v) : "l"(p) : "memory"); return v; }
__device__ __forceinline__ uint4 lds4(uint32_t a) { uint4 v; asm volatile("ld.shared.v4.u32 {%0,%1,%2,%3}, [%4];" : "=r"(v.x), "=r"(v.y), "=r"(v.z), "=r"(v.w) : "r"(a) : "memory"); return v; }
__device__ __forceinline__ float2 lds2f(uint32_t a) { float2 v; asm volatile("ld.shared.v2.f32 {%0,%1}, [%2];" : "=f"(v.x), "=f"(v.y) : "r"(a) : "memory"); return v; }
__device__ __forceinline__ uint32_t lds1(uint32_t a) { uint32_t v; asm volatile("ld.shared.u32 %0, [%1];" : "=r"(v) : "r"(a) : "memory"); return v; }
__device__ __forceinline__ void sts4(uint32_t a, uint4 v) { asm volatile("st.shared.v4.u32 [%0], {%1,%2,%3,%4};" ::"r"(a), "r"(v.x), "r"(v.y), "r"(v.z), "r"(v.w) : "memory"); }
__device__ __forceinline__ void sts2(uint32_t a, uint32_t x, uint32_t y) { asm volatile("st.shared.v2.u32 [%0], {%1,%2};" ::"r"(a), "r"(x), "r"(y) : "memory"); }
__device__ __forceinline__ void sts1(uint32_t a, uint32_t v) { asm volatile("st.shared.u32 [%0], %1;" ::"r"(a), "r"(v) : "memory"); }
__device__ __forceinline__ void stsm4(uint32_t a, uint32_t r0, uint32_t r1, uint32_t r2, uint32_t r3) {
    asm volatile("stmatrix.sync.aligned.m8n8.x4.shared.b16 [%0], {%1,%2,%3,%4};" ::"r"(a), "r"(r0), "r"(r1), "r"(r2), "r"(r3));
}
__device__ __forceinline__ uint32_t pack2(float lo, float hi) { uint32_t r; asm("cvt.rn.bf16x2.f32 %0, %1, %2;" : "=r"(r) : "f"(hi), "f"(lo)); return r; }
__device__ __forceinline__ uint32_t pack2_relu(float lo, float hi) { uint32_t r; asm("cvt.rn.relu.bf16x2.f32 %0, %1, %2;" : "=r"(r) : "f"(hi), "f"(lo)); return r; }
__device__ __forceinline__ uint32_t hfma2(uint32_t a, uint32_t b, uint32_t c) { uint32_t r; asm("fma.rn.bf16x2 %0, %1, %2, %3;" : "=r"(r) : "r"(a), "r"(b), "r"(c)); return r; }
__device__ __forceinline__ uint32_t hmul2(uint32_t a, uint32_t b) { uint32_t r; asm("mul.rn.bf16x2 %0, %1, %2;" : "=r"(r) : "r"(a), "r"(b)); return r; }
__device__ __forceinline__ float bf_lo(uint32_t v) { return __uint_as_float(v << 16); }
__device__ __forceinline__ float bf_hi(uint32_t v) { return __uint_as_float(v & 0xFFFF0000u); }
__device__ __forceinline__ float bf_round(float v) { return bf_lo(pack2(v, 0.f)); }
__device__ __forceinline__ float ex2(float x) { float r; asm("ex2.approx.ftz.f32 %0, %1;" : "=f"(r) : "f"(x)); return r; }
__device__ __forceinline__ void mma16816(float* d, uint32_t a0, uint32_t a1, uint32_t a2, uint32_t a3, uint32_t b0, uint32_t b1) {
    asm("mma.sync.aligned.m16n8k16.row.col.f32.bf16.bf16.f32 {%0,%1,%2,%3}, {%4,%5,%6,%7}, {%8,%9}, {%0,%1,%2,%3};"
        : "+f"(d[0]), "+f"(d[1]), "+f"(d[2]), "+f"(d[3]) : "r"(a0), "r"(a1), "r"(a2), "r"(a3), "r"(b0), "r"(b1));
}
__device__ __forceinline__ void mma16816_first(float* d, uint32_t a0, uint32_t a1, uint32_t a2, uint32_t a3, uint32_t b0, uint32_t b1) {
    asm volatile("mma.sync.aligned.m16n8k16.row.col.f32.bf16.bf16.f32 {%0,%1,%2,%3}, {%4,%5,%6,%7}, {%8,%9}, {%10,%10,%10,%10};"
        : "=f"(d[0]), "=f"(d[1]), "=f"(d[2]), "=f"(d[3]) : "r"(a0), "r"(a1), "r"(a2), "r"(a3), "r"(b0), "r"(b1), "f"(0.f));
}
__device__ __forceinline__ void mma16816_v(float* d, uint32_t a0, uint32_t a1, uint32_t a2, uint32_t a3, uint32_t b0, uint32_t b1) {
    asm volatile("mma.sync.aligned.m16n8k16.row.col.f32.bf16.bf16.f32 {%0,%1,%2,%3}, {%4,%5,%6,%7}, {%8,%9}, {%0,%1,%2,%3};"
        : "+f"(d[0]), "+f"(d[1]), "+f"(d[2]), "+f"(d[3]) : "r"(a0), "r"(a1), "r"(a2), "r"(a3), "r"(b0), "r"(b1));
}
__device__ __forceinline__ void mma1688(float* d, uint32_t a0, uint32_t a1, uint32_t b0) {
    asm("mma.sync.aligned.m16n8k8.row.col.f32.bf16.bf16.f32 {%0,%1,%2,%3}, {%4,%5}, {%6}, {%0,%1,%2,%3};"
        : "+f"(d[0]), "+f"(d[1]), "+f"(d[2]), "+f"(d[3]) : "r"(a0), "r"(a1), "r"(b0));
}
__device__ __forceinline__ void ldsm4(uint32_t a, uint32_t* r) {
    asm volatile("ldmatrix.sync.aligned.m8n8.x4.shared.b16 {%0,%1,%2,%3}, [%4];" : "=r"(r[0]), "=r"(r[1]), "=r"(r[2]), "=r"(r[3]) : "r"(a));
}
__device__ __forceinline__ void ldsm4t(uint32_t a, uint32_t* r) {
    asm volatile("ldmatrix.sync.aligned.m8n8.x4.trans.shared.b16 {%0,%1,%2,%3}, [%4];" : "=r"(r[0]), "=r"(r[1]), "=r"(r[2]), "=r"(r[3]) : "r"(a));
}
__device__ __forceinline__ uint32_t nz(uint32_t v) { uint32_t r; asm("max.u32 %0, %1, 1;" : "=r"(r) : "r"(v)); return r; }
__device__ __forceinline__ float rcp(float x) { float r; asm("rcp.approx.ftz.f32 %0, %1;" : "=f"(r) : "f"(x)); return r; }
__device__ __forceinline__ uint2 ld_relaxed2(const void* p) { uint2 v; asm volatile("ld.relaxed.gpu.global.v2.u32 {%0,%1}, [%2];" : "=r"(v.x), "=r"(v.y) : "l"(p) : "memory"); return v; }
__device__ __forceinline__ void st_relaxed2(void* p, uint32_t x, uint32_t y) { asm volatile("st.relaxed.gpu.global.v2.u32 [%0], {%1,%2};" ::"l"(p), "r"(max(x, 1u)), "r"(max(y, 1u)) : "memory"); }
__host__ __device__ constexpr uint64_t dconst(uint32_t lbo, uint32_t sbo, uint32_t swz) {
    return ((uint64_t)(lbo >> 4) << 16) | ((uint64_t)(sbo >> 4) << 32) | ((uint64_t)swz << 62);
}
__device__ __forceinline__ uint32_t mkdesc(uint32_t addr, uint64_t c) { return (uint32_t)c | ((addr & 0x3FFFF) >> 4); }
#define WG_FENCE() asm volatile("wgmma.fence.sync.aligned;" ::: "memory")
#define WG_COMMIT() asm volatile("wgmma.commit_group.sync.aligned;" ::: "memory")
#define WG_WAIT(n) asm volatile("wgmma.wait_group.sync.aligned %0;" ::"n"(n) : "memory")
template <int N> __device__ __forceinline__ void reg_fence(float* d) {
#pragma unroll
    for (int i = 0; i < N; i++) asm volatile("" : "+f"(d[i])::"memory");
}
template <int N> __device__ __forceinline__ void reg_def(float* d) {
#pragma unroll
    for (int i = 0; i < N; i++) asm volatile("" : "=f"(d[i]));
}
template <int N> __device__ __forceinline__ void reg_def(uint32_t* d) {
#pragma unroll
    for (int i = 0; i < N; i++) asm volatile("" : "=r"(d[i]));
}
__device__ __forceinline__ bool is_unset(uint4 v) { return min(min(v.x, v.y), min(v.z, v.w)) == 0u; }
__device__ __forceinline__ uint4 nz4(uint32_t a, uint32_t b, uint32_t c, uint32_t d) { return make_uint4(max(a, 1u), max(b, 1u), max(c, 1u), max(d, 1u)); }
__device__ __forceinline__ void wait_flags(const uint32_t* p, uint32_t target, uint32_t mask) {
    int n = 0;
    while (~__ballot_sync(~0u, (int)(ld_relaxed(p) - target) >= 0) & mask) { if (++n > SPIN_LIMIT) __trap(); }
    asm volatile("fence.acquire.gpu;" ::: "memory");
}
__device__ __forceinline__ float silu_bf(uint32_t cbits) {
    const float c = __uint_as_float(cbits << 16);
    return bf_round(__fdividef(c, 1.f + fminf(ex2(-1.4426950408889634f * c), 1e30f)));
}
__device__ __forceinline__ void gemv_part(uint32_t wmbuf, int wp, int lane) {
    const uint32_t wa = wmbuf + wp * 512 + (8 * (lane >> 4) + (lane & 7)) * 32 + ((lane >> 3) & 1) * 16;
    float d[4] = {};
#pragma unroll
    for (int i = 0; i < 4; i++) {
        uint32_t A[4];
        const float2 v = lds2f(wmbuf + 28672 + (wp + 8 * i) * 32 + (lane & 3) * 8);
        ldsm4t(wa + (i < 3 || wp < 4 ? i : 0) * 4096, A);
        mma16816(d, A[0], A[1], A[2], A[3], __float_as_uint(v.x), __float_as_uint(v.y));
    }
    if ((lane & 3) == 0) {
        sts1(wmbuf + 29696 + (wp * 16 + (lane >> 2)) * 4, __float_as_uint(d[0]));
        sts1(wmbuf + 29696 + (wp * 16 + 8 + (lane >> 2)) * 4, __float_as_uint(d[2]));
    }
}
__device__ __forceinline__ uint32_t mod_word(float v, int col, uint32_t target) {
    v = bf_round(v);
    if ((col >= DM && col < 2 * DM) || (col >= 4 * DM && col < 5 * DM)) v += 1.f;
    return (pack2(v, 0.f) << 16) | (target & 0xFFFFu);
}
__device__ __forceinline__ const uint4* mod_src(int i, int r, int j, bool p2) {
    i = min(i, p2 ? 251 : 223);
    return (const uint4*)g_mod + (r & 7) * (6 * DM / 4) + (i < 224 ? (p2 ? 336 : 0) + i : (i < 238 ? 14 * j + i : 14 * j + i + 322));
}
__device__ __forceinline__ void mod_store(uint32_t sb, uint4 v, const uint4* src, int i) {
    const uint32_t tag = lds1(sb + M_EPOCH) + 1;
    while (__any_sync(~0u, (((v.x ^ tag) | (v.y ^ tag) | (v.z ^ tag) | (v.w ^ tag)) & 0xFFFFu) != 0u)) v = ld_relaxed4(src);
    if (i < 224) {
        const int isc = i >= 112, c4 = i - 112 * isc;
        const uint32_t a = sb + M_ST + (c4 >> 2) * 64 + (c4 & 1) * 32 + (c4 & 2) * 4 + (isc ? 0 : 4);
        sts1(a, __byte_perm(v.x, v.y, 0x7632));
        sts1(a + 16, __byte_perm(v.z, v.w, 0x7632));
    } else if (i < 252) {
        sts4(sb + M_G + (i - 224) * 16, make_uint4(v.x & 0xFFFF0000u, v.y & 0xFFFF0000u, v.z & 0xFFFF0000u, v.w & 0xFFFF0000u));
    }
}
__device__ __forceinline__ int pass_f(int fs, int ps) { return 224 * fs + ((fs & 1) ? (ps == 0 ? 96 : ps == 1 ? 32 : 0) : (ps == 0 ? 0 : ps == 1 ? 128 : 192)); }
__device__ __forceinline__ constexpr uint32_t slot_off(int l) { return l * 16384; }
__device__ __forceinline__ constexpr int g1_slot(int s) { return s % 7; }
__device__ __noinline__ void x1_fix(const uint32_t* g, uint32_t sa, int s) {
#pragma unroll 1
    for (int k = 4 * s; k < 4 * s + 4;) {
        const uint4 v = ld_relaxed4((const uint4*)(g + k * 256));
        sts4(sa + k * 1024, v);
        k += 2 * __all_sync(~0u, min(min(v.x, v.y), min(v.z, v.w)) != 0u);
    }
    __syncwarp();
}
__device__ __forceinline__ void ln_coeffs(float mean, float msq, uint32_t& r2, uint32_t& n2) {
    const float rs = bf_round(rsqrtf(fmaxf(msq - mean * mean, 0.f) + 1e-5f));
    r2 = pack2(rs, rs);
    n2 = pack2(-mean * rs, -mean * rs);
}

#define LOADW bulk_e(dst, g_wd + (size_t)((f >> 5) * 4 + nq) * 1792, 7168, bar);
template <int sec> __device__ __forceinline__ void ring_loader(const Params& p, uint32_t sb_, int r_, int j_, int lane) {
    const uint32_t sb = opaque(sb_);
    const int r = opaque(r_), j = opaque(j_), nq = j >> 1, fs = 4 * (j & 1) + nq;
    const int fa = pass_f(fs, 0), fb = pass_f(fs, 1), fc = pass_f(fs, 2);
    const uint32_t* h2src = (const uint32_t*)__shfl_sync(~0u, (unsigned long long)(p.actb + (size_t)r * RB_WORDS + RB_H2), 0);
    const uint32_t* hcsrc = h2src + (RB_HC - RB_H2) + opaque((lds1(sb + M_EPOCH) & 1) * 8 + (j & 1)) * 2048;
    const CUtensorMap* gmap = (const CUtensorMap*)__shfl_sync(~0u, (unsigned long long)(&p.ga + sec), 0);
#define BAR(i) (sb + M_BAR + 8 * (i))
#define kh (j & 1)
            int sl = 0;
#pragma unroll 1
            for (int s = 0; s < 28; s++) {
                if (s == 7) { wait_flags(g_flag + (8 * r + j) * 128 + 96 + lane, lds1(sb + M_EPOCH) + 1, 0xFFFFu); fence_async_global(); }
                const int ps = s < 14 ? 0 : s < 21 ? 1 : 2;
                const uint32_t half = ps < 2 ? 8192 : 4096;
                const int sp = sl;
                if (s >= PACE && s < PACE_END) mbar_wait(BAR(B_FULL + s - PACE), 0);
                mbar_wait(BAR(B_EMPTY + sp), (s >= 7 && s < 14) || s >= 21);
                const uint32_t bar = BAR(B_FULL + sp);
                expect_e(bar, ps == 2 && (s & 1) == sec ? half + 7168 : half);
                tma3_e(sb + slot_off(sp) + sec * half, gmap + 2 * ps, 0, ps ? 64 * sl : 32 * s, ps == 0 ? fa >> 6 : ps == 1 ? fb >> 6 : fc >> 5, bar);
                if (ps == 2 && (s & 1) == sec) {
                    const uint32_t dst = sb + slot_off(sp) + 8192;
                    const int f = sl < 4 ? fa + 32 * sl : sl < 6 ? fb + 32 * (sl - 4) : fc;
                    LOADW
                }
                sl = sl == 6 ? 0 : sl + 1;
            }
            if (!sec) PROFH(3);
            int e = 0;
#pragma unroll 1
            for (int grp = 0; grp < 9; grp++) {
                const int ps = grp >= 6 ? 2 : grp >= 3 ? 1 : 0;
                int sidx = grp - 3 * ps;
                if (sec && sidx == 0) { mbar_wait(BAR(B_HRDY + ps), 0); fence_async_global(); }
                sidx += sidx >= nq;
                int f = pass_f(4 * kh + sidx, ps);
#pragma unroll 1
                for (int k = 4 >> ps; k > 0; k--, e++, f += 32) {
                    const uint32_t dst = sb + slot_off(sl), bar = BAR(B_FULL + sl);
                    mbar_wait(BAR(B_EMPTY + sl), e >= 12);
                    if (e >= WIN) mbar_wait(BAR(B_FULL + (sl >= WIN ? sl - WIN : sl + 12 - WIN)), e - WIN >= 12);
                    expect_e(bar, sec ? 8192 : 7168);
                    if (!sec) { LOADW }
                    else bulk_e(dst + 8192, ps < 2 ? h2src + f * 64 : hcsrc + sidx * 4096, 8192, bar);
                    sl = sl == 11 ? 0 : sl + 1;
                }
            }
            if (!sec) PROFH(4);
}

#define PROF_PARAMS
#define PROF_ARGS
__device__ __noinline__ void helper_late(const Params& p, int r_, int j_, int warp_ PROF_PARAMS) {
    extern __shared__ __align__(1024) unsigned char smem[];
    const uint32_t sb = (uint32_t)__cvta_generic_to_shared(smem);
    const int r = opaque(r_), j = opaque(j_), warp = opaque(warp_), nq = j >> 1, b = 8 * r + j;
    uint32_t* const act = (uint32_t*)__shfl_sync(~0u, (unsigned long long)(p.actb + (size_t)r * RB_WORDS), 0);
    {
        const int lane = fresh_tid() & 31;
        const uint32_t target = lds1(sb + M_EPOCH) + 1;
        if (warp == 8) { expect_e(BAR(B_XCH), 14336); expect_e(BAR(B_XCH + 1), 14336); }
            if (warp == 9) {
#pragma unroll 1
                for (int kv = 0; kv < 2; kv++) {
                    mbar_wait(BAR(B_PUB + kv), 0);
                    wait_flags(g_flag + b * 128 + lane, target, (r >= 2 ? 6u : r == 1 ? 2u : 0u) << (8 * kv));
                    fence_async_global();
                    const uint32_t dst = sb + OFF_Y + (kv ? Y_VR : Y_K);
                    expect_e(BAR(B_KRFULL + kv), r >= 2 ? 28672 : r == 1 ? 14336 : 0);
                    if (r >= 2) bulk_e(dst, act - 2 * RB_WORDS + RB_KV + j * 7168 + kv * 3584, 14336, BAR(B_KRFULL + kv));
                    if (r >= 1) bulk_e(dst + 14336, act - RB_WORDS + RB_KV + j * 7168 + kv * 3584, 14336, BAR(B_KRFULL + kv));
                }
            } else if (warp == 8) {
                uint4 v[8];
                mbar_wait(BAR(B_WOFULL), 0);
#pragma unroll
                for (int k = 0; k < 8; k++) v[k] = ld_relaxed4(mod_src(lane + 32 * k, r, j, true));
#pragma unroll
                for (int k = 0; k < 8; k++) mod_store(sb, v[k], mod_src(lane + 32 * k, r, j, true), lane + 32 * k);
                warp_arrive(BAR(B_MOD1));
            } else if (warp == 11) {
                if (kh == 1 && r < 14) {
                    const uint32_t wmbuf = sb + OFF_X + HALF;
                    const int mcol = 2 * DM + 32 * (4 * r + nq);
                    mbar_wait(BAR(B_XFREE), 0);
#pragma unroll 1
                    for (int k = 0; k < 4; k++) tma3_e(wmbuf + k * 7168, &p.wm, mcol + (k >> 1) * 16, (k & 1) * 224, 0, BAR(B_WMFULL));
#pragma unroll 1
                    for (int wd = lane; wd < 224; wd += 32) {
                        const uint32_t cb = __ldg((const uint32_t*)p.c + wd);
                        sts1(wmbuf + 28672 + (wd >> 3) * 32 + (wd & 3) * 8 + (wd & 4), pack2(silu_bf(cb & 0xFFFFu), silu_bf(cb >> 16)));
                    }
                    __syncwarp();
                    mbar_wait(BAR(B_WMFULL), 0);
                    const uint32_t wa = wmbuf + (8 * (lane >> 4) + (lane & 7)) * 32 + ((lane >> 3) & 1) * 16;
                    float d[2][4] = {};
#pragma unroll 4
                    for (int ks = 0; ks < 28; ks++) {
                        uint32_t A[8];
                        ldsm4t(wa + ks * 512, A); ldsm4t(wa + 14336 + ks * 512, A + 4);
                        const float2 v = lds2f(wmbuf + 28672 + ks * 32 + (lane & 3) * 8);
                        mma16816(d[0], A[0], A[1], A[2], A[3], __float_as_uint(v.x), __float_as_uint(v.y));
                        mma16816(d[1], A[4], A[5], A[6], A[7], __float_as_uint(v.x), __float_as_uint(v.y));
                    }
                    const int q = lane & 3, col = mcol + 8 * q + (lane >> 2);
                    const uint32_t word = mod_word(q == 0 ? d[0][0] : q == 1 ? d[0][2] : q == 2 ? d[1][0] : d[1][2], col, target);
#pragma unroll
                    for (int i = 0; i < 8; i++) st_relaxed(g_mod + i * 6 * DM + col, word);
                }
                warp_arrive(BAR(B_WMFREE));
                mbar_wait(BAR(B_VRFULL), 0);
                l2_prefetch_e((const char*)p.wg + (size_t)b * 12544, 12544);
                l2_prefetch_e((const char*)p.wu + (size_t)b * 12544, 12544);
#pragma unroll 1
                for (int k = 0; k < (r < 12 ? 2 : 1); k++) {
                    const int u = 28 * kh + r + 16 * k;
                    expect_e(BAR(B_XFULL + k), 7168);
                    tma3_e(sb + OFF_Y + 102400, &p.dn, 0, 32 * u, 7 * j, BAR(B_XFULL + k));
                    tma3_e(sb + OFF_Y + 102400 + 3584, &p.dn, 0, 32 * u, 7 * (j ^ 1), BAR(B_XFULL + k));
                    mbar_wait(BAR(B_XFULL + k), 1);
                    asm volatile("{\n.reg .pred p;\nelect.sync _|p, 0xffffffff;\n@p cp.async.bulk.global.shared::cta.bulk_group [%0], [%1], 7168;\n"
                                 "cp.async.bulk.commit_group;\ncp.async.bulk.wait_group 0;\n}" ::"l"(g_wd + (size_t)(u * 4 + nq) * 1792), "r"(sb + OFF_Y + 102400) : "memory");
                    __syncwarp();
                }
                warp_arrive(BAR(B_FULLK));
                fence_gpu();
                if (lane < 16) st_relaxed(g_flag + (8 * lane + j) * 128 + 96 + r, target);
            }
        if (warp == 8 || warp == 11) {
            const int sec = warp == 11;
            if (sec) ring_loader<1>(p, sb, r, j, lane); else ring_loader<0>(p, sb, r, j, lane);
            mbar_wait(BAR(B_DONE), 0);
        } else if (warp == 9) {
#pragma unroll
            for (int ev = 0; ev < 4; ev++) { expect_e(BAR(B_GFULL + ev), ev < 2 ? HALF / 2 : 16384 + 4096); expect_e(BAR(B_XFULL + 2 + ev), ev < 2 ? HALF / 2 : HALF - 16384); }
            mbar_wait(BAR(B_PUB + 2), 0);
            const uint32_t* fp = g_flag + b * 128 + 32 + lane;
            const int par = (target - 1) & 1;
#pragma unroll 1
            for (int n = 0, ev = 0; ev < 4; n++) {
                if (ev == 1) mbar_wait(BAR(B_PUB + 3), 0);
                uint32_t ok = __ballot_sync(~0u, (int)(ld_relaxed(fp) - target) >= 0) >> (8 * ev);
                while ((ok & 0xFFu) == 0xFFu) {
                    if (ev == 1) mbar_wait(BAR(B_FULLK), 1);
                    asm volatile("fence.acquire.gpu;" ::: "memory");
                    fence_async_global();
                    const int tile = (ev & 1) + (ev >> 1) * par * 2;
                    const uint32_t dst = sb + (ev == 0 ? OFF_X : OFF_Y + (ev & 1) * HALF), first = ev < 2 ? HALF / 2 : 16384;
                    const char* src = (const char*)(act + RB_O + ((ev >> 1) * 2 + tile) * 14336);
                    if (ev >= 2) bulk_e(sb + OFF_X + X_STAT + (ev & 1) * 49152, act + RB_ST + tile * 1024, 4096, BAR(B_GFULL + ev));
                    bulk_e(dst, src, first, BAR(B_GFULL + ev));
                    bulk_e(dst + first, src + first, HALF - first, BAR(B_XFULL + 2 + ev));
                    if (ev) PROFH(4 + ev);
                    ev++; ok >>= 8;
                }
                if (n > SPIN_LIMIT) __trap();
            }
            mbar_wait(BAR(B_XFULL + 5), 1);
#pragma unroll 1
            for (int hf = 0; hf < 2; hf++) {
                const int tile = (par ^ 1) * 2 + hf;
                uint4* xz = (uint4*)(act + RB_X1 + tile * 14336 + j * 1792) + lane;
#pragma unroll
                for (int i = 0; i < 14; i++) xz[i * 32] = make_uint4(0, 0, 0, 0);
                ((uint4*)(act + RB_ST + (tile * 8 + j) * 128))[lane] = make_uint4(0, 0, 0, 0);
                uint4* hz = (uint4*)(act + RB_HC + ((par ^ 1) * 8 + j) * 2048 + hf * 1024) + lane;
#pragma unroll
                for (int i = 0; i < 8; i++) hz[i * 32] = make_uint4(0, 0, 0, 0);
            }
#pragma unroll 1
            for (int ps = 0; ps < 3; ps++) {
                mbar_wait(BAR(B_PUB + 6 + ps), 0);
                wait_flags(g_flag + b * 128 + 64 + lane, target, (0x55u << kh) << (8 * ps));
                warp_arrive(BAR(B_HRDY + ps));
                PROFH(9 + ps);
            }
        } else {
#pragma unroll 1
            for (int k = 0; k < 9; k++) {
                uint32_t* fp = k < 2 ? g_flag + (b + 8 * lane) * 128 + k * 8 + lane : g_flag + (8 * r + lane) * 128 + 16 + k * 8 + j;
                mbar_wait(BAR(B_PUB + k), 0);
                if (k != 4 && k != 5 && k != 8) fence_gpu();
                if (k < 2 ? (lane == 1 || lane == 2) : lane < 8) st_relaxed(fp, target);
                if (k >= 3 && k <= 5) PROFH(k - 3);
            }
        }
    }
}

__global__ void __cluster_dims__(2, 1, 1) __launch_bounds__(384, 1) fused_block_kernel(const __grid_constant__ Params p) {
    extern __shared__ __align__(1024) unsigned char smem[];
    const uint32_t sb = (uint32_t)__cvta_generic_to_shared(smem);
    const int tid = threadIdx.x, lane = tid & 31, warp = __shfl_sync(~0u, tid >> 5, 0);
    const int m = blockIdx.x >> 1;
    int r, nq;
    if (m < 4) { r = 15; nq = m; }
    else if (m < 36) { r = (m - 4) & 7; nq = (m - 4) >> 3; }
    else { nq = (m - 36) / 7; r = m - 28 - 7 * nq; }
    const int j = opaque(2 * nq + (blockIdx.x & 1)), b = 8 * r + j, fs = 4 * kh + nq;
#define act (p.actb + (size_t)r * RB_WORDS)
    constexpr uint32_t sc = 0;
    if (lane == 0 && warp < 9 && warp != 6 && warp != 7) {
        const int i0 = warp == 8 ? 0 : 8 + 8 * warp, cnt = warp == 0 || warp == 8 ? 1 : warp < 3 ? 2 : 8;
#pragma unroll
        for (int k = 0; k < 8; k++) if (i0 + k != B_WMFULL) mbar_init(BAR(i0 + k), cnt);
        asm volatile("fence.mbarrier_init.release.cluster;" ::: "memory");
        fence_async_smem();
    }

    if (warp >= 8) {
        const int lane = fresh_tid() & 31;
        const bool early = kh == 0, gemv = r < 14;
        const int mcol = early ? 16 * (4 * r + nq) : 2 * DM + 32 * (4 * r + nq);
        const uint32_t wmbuf = sb + OFF_Y + HALF;
        asm volatile("setmaxnreg.dec.sync.aligned.u32 56;");
        if (warp == 9) {
#pragma unroll
            for (int i = 56; i < 64; i++) init_e(BAR(i), 1);
            fence_async_smem();
        }
        if (warp == 8) { init_e(BAR(B_WMFULL), 1); fence_async_smem(); }
        bar_arrive(0, 384);
        asm volatile("barrier.cluster.arrive.relaxed.aligned;" ::: "memory");
        if (warp == 8) {
            if (!sc) {
                expect_e(BAR(B_WMFULL), gemv ? 28672 >> early : 0);
                if (early && gemv) { tma3_e(wmbuf, &p.wm, mcol, 0, 0, BAR(B_WMFULL)); tma3_e(wmbuf + 7168, &p.wm, mcol, 224, 0, BAR(B_WMFULL)); }
#pragma unroll 1
                for (int kb = 0; kb < 7; kb++) {
                    expect_e(BAR(B_XFULL + kb), 16384);
                    tma3_e(sb + OFF_X + kb * 16384, &p.xm, 64 * kb, 128 * r, 0, BAR(B_XFULL + kb));
                }
            }
#pragma unroll 1
            for (int mt = 0; mt < 4; mt++) {
                if (mt == 1) bar_sync(9, 384);
                if (mt == 3) mbar_wait(BAR(B_WMFREE), 0);
                if (mt) mbar_wait(BAR(mt == 1 ? B_MOD1 : mt == 2 ? B_XFREE : B_VRFULL), 0);
                const uint32_t bar = BAR(mt == 3 ? B_WOFULL : B_FULLK + mt), dst = sb + (mt < 2 ? OFF_Y : OFF_X) + (mt & 1) * HALF;
                const int c0 = (mt < 2 ? DM + DM * mt : 0) + 56 * j - 8 * kh;
                if (!sc) {
                    expect_e(bar, HALF);
                    tma3_e(dst, mt == 3 ? &p.wo : &p.qkv, c0, 0, 0, bar);
                    tma3_e(dst + HALF / 2, mt == 3 ? &p.wo : &p.qkv, c0, 224, 0, bar);
                }
            }
        } else {
            if (warp == 10 && !sc) l2_prefetch_e((const char*)p.wqkv + (size_t)b * 9408, 9408);
            bar_sync(9, 384);
            if (sc) return;
            if (warp == 11 && early) {
                const uint32_t target = lds1(sb + M_EPOCH) + 1;
                mbar_wait(BAR(B_GEMV), 0);
                float sum = 0.f;
#pragma unroll
                for (int i = 0; i < 8; i++) sum += *(const float*)(smem + OFF_Y + HALF + 29696 + (i * 16 + (lane & 15)) * 4);
                uint32_t* mg = g_mod + mcol + (lane & 15) + (lane >> 4) * 4 * 6 * DM;
                const uint32_t word = mod_word(sum, mcol, target);
                if (gemv) { st_relaxed(mg, word); st_relaxed(mg + 6 * DM, word); st_relaxed(mg + 12 * DM, word); st_relaxed(mg + 18 * DM, word); }
            }
        }
    }
    if (LIKELY(warp < 8)) {
        const int w = warp >> 2, wi = warp & 3;
#define COORDS const int t = fresh_tid() & 127, lane = t & 31, q = lane & 3, lr = lane >> 2, ra = 64 * w + 16 * wi + lr; \
        const uint32_t lx = (lane >> 4) ^ (lane & 7), mrow = (64 * w + 16 * wi + ((lane >> 3) & 1) * 8 + (lane & 7)) * 128; \
        (void)q; (void)lr; (void)ra; (void)lx; (void)mrow;
        const int sid = 2 * (j & 3) + w;
#define RUN(k) (!sc || sid == (k))
#define WAIT(i, par) mbar_wait_c(BAR(i), (par) | sc)
        constexpr uint64_t DB128 = dconst(4096, 1024, 1);
        {
            const int wd = fresh_tid();
            const uint32_t cb = wd < 224 ? __ldg((const uint32_t*)p.c + wd) : 0u;
            if (wd == 255 && !sc) sts1(sb + M_EPOCH, atomicAdd(&g_ticket, 1u) / NCTA);
            sts1(sb + OFF_Y + HALF + 28672 + (wd >> 3) * 32 + (wd & 3) * 8 + (wd & 4), pack2(silu_bf(cb & 0xFFFFu), silu_bf(cb >> 16)));
        }
        bar_arrive(9, 384);
        bar_sync(0, 384);
        asm volatile("barrier.cluster.arrive.relaxed.aligned;" ::: "memory");
        asm volatile("setmaxnreg.inc.sync.aligned.u32 224;");
        PROFC(0);
        uint32_t xr[16];
        {
            COORDS
            uint32_t h[112];
            uint32_t ra2, na2, rb2, nb2;
            const int mi = min(128 * w + t, 223);
            const uint4* msrc = mod_src(mi, r, j, false);
            uint4 mv;
            {
                float ds[4] = {}, da[2][4] = {}, db[2][4] = {};
                const uint32_t ONE2 = 0x3F803F80u;
#pragma unroll
                for (int kb = 0; kb < 7; kb++) {
                    if (kb == GEMV_AT && kh == 0) { WAIT(B_WMFULL, 0); gemv_part(sb + OFF_Y + HALF, warp, lane); warp_arrive(BAR(B_GEMV)); }
                    WAIT(B_XFULL + kb, 0);
#pragma unroll
                    for (int k4 = 0; k4 < 4; k4++) ldsm4(sb + OFF_X + mrow + kb * 16384 + (((2 * k4) ^ lx) << 4), h + 16 * kb + 4 * k4);
#pragma unroll
                    for (int k4 = 0; k4 < 4; k4++) {
                        const uint32_t* f = h + 16 * kb + 4 * k4;
                        mma16816(ds, f[0], f[1], f[2], f[3], ONE2, ONE2);
                        mma1688(da[0], f[0], f[1], f[0]); mma1688(db[0], f[0], f[1], f[1]);
                        mma1688(da[1], f[2], f[3], f[2]); mma1688(db[1], f[2], f[3], f[3]);
                    }
                }
#pragma unroll
                for (int i = 0; i < 4; i++) {
                    const int ch = 7 * j + 2 * i + (lane >> 4);
                    ldsm4(sb + OFF_X + mrow + (ch >> 3) * 16384 + (((ch ^ lane) & 7) << 4), xr + 4 * i);
                }
                mv = ld_relaxed4(msrc);
                warp_arrive(BAR(B_XFREE));
                float qa = (lr & 1) ? da[0][1] + da[1][1] : da[0][0] + da[1][0];
                float qb = (lr & 1) ? db[0][3] + db[1][3] : db[0][2] + db[1][2];
                const int src = (lane & ~3) | (lr >> 1);
                qa = __shfl_sync(~0u, qa, src);
                qb = __shfl_sync(~0u, qb, src);
                ln_coeffs(ds[0] * (1.f / DM), qa * (1.f / DM), ra2, na2);
                ln_coeffs(ds[2] * (1.f / DM), qb * (1.f / DM), rb2, nb2);
#pragma unroll
                for (int i = 0; i < 4 * NPRE; i += 2) { h[i] = hfma2(h[i], ra2, na2); h[i + 1] = hfma2(h[i + 1], rb2, nb2); }
            }
            PROFC(1);
            {
                float ak[28], av[28], aq[28];
                uint32_t kp[14], vp[14];
                const uint64_t bq0 = (DB128 & ~0xFFFFFFFFull) | (mkdesc(sb + OFF_X, DB128) + kh), bk0 = bq0 + (OFF_Y >> 4), bv0 = bk0 + (HALF >> 4);
                uint32_t* kvg = act + RB_KV + j * 7168 + (8 * w + 2 * wi) * 224 + lane;
                mod_store(sb, mv, msrc, mi);
                bar_sync(3, 256);
                if (warp == 0) warp_arrive(BAR(B_MOD1));
                WAIT(B_FULLK, 0);
                PROFC(2);
                reg_def<28>(ak);
#pragma unroll
                for (int g4 = 0; g4 < 4; g4++) {
#pragma unroll
                    for (int ks = 7 * g4; ks < 7 * g4 + 7; ks++) {
                        const uint4 st = *(const uint4*)(smem + M_ST + ks * 64 + q * 16);
                        if (ks >= NPRE) {
                            h[4 * ks] = hfma2(h[4 * ks], ra2, na2); h[4 * ks + 1] = hfma2(h[4 * ks + 1], rb2, nb2);
                            h[4 * ks + 2] = hfma2(h[4 * ks + 2], ra2, na2); h[4 * ks + 3] = hfma2(h[4 * ks + 3], rb2, nb2);
                        }
                        h[4 * ks] = hfma2(h[4 * ks], st.x, st.y); h[4 * ks + 1] = hfma2(h[4 * ks + 1], st.x, st.y);
                        h[4 * ks + 2] = hfma2(h[4 * ks + 2], st.z, st.w); h[4 * ks + 3] = hfma2(h[4 * ks + 3], st.z, st.w);
                    }
                    WG_FENCE();
#pragma unroll
                    for (int ks = 7 * g4; ks < 7 * g4 + 7; ks++) wgmma_rl_56(ak, h[4 * ks], h[4 * ks + 1], h[4 * ks + 2], h[4 * ks + 3], bk0 + ks * 128, ks != 0);
                }
                WG_COMMIT();
                PROFC(3);
                WAIT(B_FULLV, 0);
                reg_def<28>(av);
                WG_FENCE();
#pragma unroll
                for (int ks = 0; ks < 8; ks++) wgmma_rl_56(av, h[4 * ks], h[4 * ks + 1], h[4 * ks + 2], h[4 * ks + 3], bv0 + ks * 128, ks != 0);
                WG_COMMIT();
                WG_WAIT(1);
                reg_fence<28>(ak);
#pragma unroll
                for (int g = 0; g < 7; g++) {
                    kp[2 * g] = pack2(ak[4 * g], ak[4 * g + 1]); kp[2 * g + 1] = pack2(ak[4 * g + 2], ak[4 * g + 3]);
                    kvg[g * 32] = kp[2 * g]; kvg[224 + g * 32] = kp[2 * g + 1];
                }
                warp_arrive(BAR(B_PUB));
                PROFC(4);
                WG_FENCE();
#pragma unroll
                for (int ks = 8; ks < 28; ks++) wgmma_rl_56(av, h[4 * ks], h[4 * ks + 1], h[4 * ks + 2], h[4 * ks + 3], bv0 + ks * 128, 1);
                WG_COMMIT();
                WAIT(B_FULLQ, 0);
                reg_def<28>(aq);
                WG_FENCE();
#pragma unroll
                for (int ks = 0; ks < 8; ks++) wgmma_rl_56(aq, h[4 * ks], h[4 * ks + 1], h[4 * ks + 2], h[4 * ks + 3], bq0 + ks * 128, ks != 0);
                WG_COMMIT();
                WG_WAIT(1);
                reg_fence<28>(av);
#pragma unroll
                for (int g = 0; g < 7; g++) {
                    vp[2 * g] = pack2(av[4 * g], av[4 * g + 1]); vp[2 * g + 1] = pack2(av[4 * g + 2], av[4 * g + 3]);
                    kvg[3584 + g * 32] = vp[2 * g]; kvg[3584 + 224 + g * 32] = vp[2 * g + 1];
                }
                warp_arrive(BAR(B_PUB + 1));
                PROFC(5);
                WG_FENCE();
#pragma unroll
                for (int ks = 8; ks < 28; ks++) wgmma_rl_56(aq, h[4 * ks], h[4 * ks + 1], h[4 * ks + 2], h[4 * ks + 3], bq0 + ks * 128, 1);
                WG_COMMIT();
                WAIT(B_PUB + 1, 0);
                const uint32_t rg = 8 * w + 2 * wi + ((lane >> 3) & 1);
                const uint32_t ko = sb + OFF_Y + Y_KOWN + rg * 896 + (lane & 7) * 16, qo = sb + OFF_Y + Y_Q + rg * 1024 + (lane >> 4) * 128 + (lane & 7) * 16;
#pragma unroll
                for (int g = 0; g < 6; g += 2) {
                    stsm4(ko + (g + (lane >> 4)) * 128, kp[2 * g], kp[2 * g + 1], kp[2 * g + 2], kp[2 * g + 3]);
                    stsm4(ko + (Y_VOWN - Y_KOWN) + (g + (lane >> 4)) * 128, vp[2 * g], vp[2 * g + 1], vp[2 * g + 2], vp[2 * g + 3]);
                }
                stsm4(ko + (lane >> 4) * (Y_VOWN - Y_KOWN) + 6 * 128, kp[12], kp[13], vp[12], vp[13]);
                WG_WAIT(0);
                reg_fence<28>(aq);
                __syncwarp();
                if (lane < 3 && w == 1) mbar_arrive(BAR(B_EMPTY + lane));
                uint32_t qp[14];
#pragma unroll
                for (int i = 0; i < 14; i++) qp[i] = pack2(aq[2 * i], aq[2 * i + 1]);
                stsm4(qo, qp[0], qp[1], qp[2], qp[3]);
                stsm4(qo + 256, qp[4], qp[5], q < 2 ? qp[6] : 0u, q < 2 ? qp[7] : 0u);
                stsm4(qo + 512, q < 2 ? 0u : qp[6], q < 2 ? 0u : qp[7], qp[8], qp[9]);
                stsm4(qo + 768, qp[10], qp[11], qp[12], qp[13]);
                if (!sc) bar_sync(3, 256);
            }
        }
        PROFC(6);
        WAIT(B_KRFULL, 0);
        PROFC(7);
        if (RUN(2)) {
#pragma unroll 1
            for (int hf = sc; hf < 2; hf++) {
                COORDS
                float s[136];
                float na = 0.f, nb = 0.f;
                const float CS = 0.18898223650461361f * 1.4426950408889634f;
                const int kg0 = 8 * hf + 2 * wi;
                const int pmin = 16 - 8 * r - 4 * hf - wi;
                const float NEG = __int_as_float(0xFF800000);
                {
                    uint32_t F[8];
                    const uint32_t qa = sb + OFF_Y + Y_Q + (kg0 + ((lane >> 3) & 1)) * 1024 + (4 * w + (lane >> 4)) * 128 + (lane & 7) * 16;
                    ldsm4(qa, F); ldsm4(qa + 256, F + 4);
                    uint32_t ka = sb + OFF_Y + Y_K + kg0 * 896 + (3 * w + (lane >> 3)) * 128 + (lane & 7) * 16;
#pragma unroll
                    for (int g = 0; g < 34; g++) {
                        uint32_t B[4];
                        if (g >= 12 && g % 4 == 0) ka += __float_as_uint(s[4 * (g - 12)]) & p.zero;
                        ldsm4(ka + g * 896, B);
                        mma16816_first(s + 4 * g, F[0], F[1], F[2], F[3], B[0], B[1]);
                        mma16816_v(s + 4 * g, F[4], F[5], F[6], F[7], B[2], B[3]);
                    }
                    const bool c0 = 2 * q > lr, c1 = 2 * q + 1 > lr;
                    if (!c0) { s[0] = NEG; s[6] = NEG; }
                    if (!c1) { s[1] = NEG; s[7] = NEG; }
                    s[2] = NEG; s[3] = NEG;
                    if (c0) { s[128] = NEG; s[134] = NEG; }
                    if (c1) { s[129] = NEG; s[135] = NEG; }
                    s[132] = NEG; s[133] = NEG;
                    float ma = NEG, mb = NEG;
#pragma unroll
                    for (int pp = 0; pp < 17; pp++) {
                        const float* e = s + 8 * pp;
                        const float bias = pp < pmin ? NEG : 0.f;
                        ma = fmaxf(ma, fmaxf(fmaxf(e[0], e[1]), fmaxf(e[4], e[5])) + bias);
                        mb = fmaxf(mb, fmaxf(fmaxf(e[2], e[3]), fmaxf(e[6], e[7])) + bias);
                    }
                    ma = fmaxf(ma, __shfl_xor_sync(~0u, ma, 1)); mb = fmaxf(mb, __shfl_xor_sync(~0u, mb, 1));
                    ma = fmaxf(ma, __shfl_xor_sync(~0u, ma, 2)); mb = fmaxf(mb, __shfl_xor_sync(~0u, mb, 2));
                    na = -ma * CS; nb = -mb * CS;
                }
                PROFC(8 + 3 * hf);
                {
                    WAIT(B_VRFULL, 0);
                    float o[16] = {}, rs[4] = {};
                    uint32_t pk[2];
                    const uint32_t va = sb + OFF_Y + Y_VR + (kg0 + ((lane >> 3) & 1)) * 896 + (3 * w + (lane >> 4)) * 128 + (lane & 7) * 16;
#pragma unroll
                    for (int pp = 0; pp < 17; pp++) {
                        uint32_t B[8];
                        const uint32_t v = va + pp * 1792 + (pp == 16 || (pp >= 9 && kg0 + 2 * pp >= 32) ? Y_VOWN - 32 * 896 : 0);
                        ldsm4t(v, B); ldsm4t(v + 256, B + 4);
                        float e[8];
                        const float bias = __uint_as_float((pp < pmin ? 0xFF800000u : 0u) | ((pp < 2 ? B[0] : pk[pp & 1]) & p.zero));
#pragma unroll
                        for (int i = 0; i < 8; i++) e[i] = ex2(fmaf(s[8 * pp + i], CS, ((i & 2) ? nb : na) + bias));
                        const uint32_t p0 = pack2(e[0], e[1]), p1 = pack2(e[2], e[3]), p2 = pack2(e[4], e[5]), p3 = pack2(e[6], e[7]);
                        pk[pp & 1] = p3;
                        mma16816(rs, p0, p1, p2, p3, 0x3F803F80u, 0x3F803F80u);
#pragma unroll
                        for (int g = 0; g < 4; g++) mma16816(o + 4 * g, p0, p1, p2, p3, B[2 * g], B[2 * g + 1]);
                    }
                    PROFC(9 + 3 * hf);
                    const float ia = rcp(rs[0]), ib = rcp(rs[2]);
                    uint32_t* og = act + RB_O + hf * 14336 + (7 * j + 3 * w) * 256 + wi * 64 + lane;
#pragma unroll
                    for (int g = 0; g < 4; g++) {
                        if ((g == 3 - 3 * w) ? ((q >> 1) == w) : true) {
                            og[g * 256] = pack2(o[4 * g] * ia, o[4 * g + 1] * ia);
                            og[g * 256 + 32] = pack2(o[4 * g + 2] * ib, o[4 * g + 3] * ib);
                        }
                    }
                    warp_arrive(BAR(B_PUB + 2 + hf));
                    PROFC(10 + 3 * hf);
                }
            }
        }
        uint32_t x1p[14];
        COORDS
        constexpr uint64_t DT = dconst(1024, 128, 0);
        const int tile = opaque((lds1(sb + M_EPOCH) & 1) * 2 + w);
        if (RUN(4)) {
            float ac[28];
            const uint32_t ad = mkdesc(sb + (w ? OFF_Y + HALF : OFF_X), DT), bd = mkdesc(sb + OFF_X + HALF, DB128) + kh;
            WAIT(B_WOFULL, 0);
            WAIT(B_MOD1, 1);
            WAIT(B_GFULL + w, 0);
            PROFC(28);
            reg_def<28>(ac);
#pragma unroll 1
            for (int u = 0; u < 4; u++) {
                if (u == 2) WAIT(B_XFULL + 2 + w, 1);
                WG_FENCE();
#pragma unroll
                for (int i = 0; i < 7; i++) wgmma_ss_56<DT, DB128>(ac, ad + (7 * u + i) * 128, bd + (7 * u + i) * 128, (u | i) != 0);
            }
            WG_COMMIT();
            WG_WAIT(0);
            reg_fence<28>(ac);
            PROFC(14);
            __syncwarp();
            if (lane < 3) mbar_arrive(BAR(B_EMPTY + 4 - w + lane));
            if (lane < 3 && w == 0) mbar_arrive(BAR(B_EMPTY + lane));
            float ds[4] = {}, da[4] = {}, db[4] = {};
            uint32_t* xo = act + RB_X1 + tile * 14336 + 7 * j * 256 + wi * 64 + lane;
#pragma unroll
            for (int g = 0; g < 7; g++) {
                const float2 ga = *(const float2*)(smem + M_G + (8 * g + 2 * q) * 4);
                x1p[2 * g] = pack2(fmaf(ga.x, ac[4 * g], bf_lo(xr[2 * g])), fmaf(ga.y, ac[4 * g + 1], bf_hi(xr[2 * g])));
                x1p[2 * g + 1] = pack2(fmaf(ga.x, ac[4 * g + 2], bf_lo(xr[2 * g + 1])), fmaf(ga.y, ac[4 * g + 3], bf_hi(xr[2 * g + 1])));
                st_relaxed(xo + g * 256, nz(x1p[2 * g])); st_relaxed(xo + g * 256 + 32, nz(x1p[2 * g + 1]));
                mma1688(ds, x1p[2 * g], x1p[2 * g + 1], 0x3F803F80u);
                mma1688(da, x1p[2 * g], x1p[2 * g + 1], x1p[2 * g]);
                mma1688(db, x1p[2 * g], x1p[2 * g + 1], x1p[2 * g + 1]);
            }
            const int src = (lane & ~3) | (lr >> 1);
            const float qa = __shfl_sync(~0u, (lr & 1) ? da[1] : da[0], src), qb = __shfl_sync(~0u, (lr & 1) ? db[3] : db[2], src);
            const float kk = (q & 1) ? ((q & 2) ? qb : qa) : ((q & 2) ? ds[2] : ds[0]);
            st_relaxed(act + RB_ST + ((tile * 8 + j) * 64 + 16 * wi + lr + 4 * (q & 2)) * 2 + (q & 1), nz(__float_as_uint(kk)));
            __syncwarp();
            if (lane < 2) mbar_arrive(BAR(B_PUB + 4 + w));
        } else reg_def<14>(x1p);
        PROFC(15);
        uint32_t h2a[32], h2b[24];
        {
            const int fa = pass_f(fs, 0), fb = pass_f(fs, 1), fc = pass_f(fs, 2);
            uint32_t* h2g = act + RB_H2 + (8 * w + 2 * wi) * 32 + lane;
            const uint32_t a0 = mkdesc(sb + OFF_Y + w * HALF, DT);
            if (RUN(3)) {
                uint32_t ra2, na2, rb2, nb2;
                {
                    const uint32_t* sg = act + RB_ST + ((tile * 8 + 2 * q) * 64 + 16 * wi + lr) * 2;
                    uint2 u[4];
                    WAIT(B_GFULL + 2 + w, 0);
                    PROFC(16);
#pragma unroll
                    for (int i = 0; i < 4; i++) { const float2 v = lds2f(sb + OFF_X + X_STAT + w * 49152 + ((2 * q + (i >> 1)) * 64 + 16 * wi + lr + 8 * (i & 1)) * 8); u[i] = make_uint2(__float_as_uint(v.x), __float_as_uint(v.y)); }
                    while (__any_sync(~0u, min(min(min(u[0].x, u[0].y), min(u[1].x, u[1].y)), min(min(u[2].x, u[2].y), min(u[3].x, u[3].y))) < 1u - sc)) {
#pragma unroll
                        for (int i = 0; i < 4; i++) u[i] = ld_relaxed2(sg + (i >> 1) * 128 + (i & 1) * 16);
                    }
                    warp_arrive(BAR(B_EMPTY + 3 + 3 * w));
                    float v[4] = {__uint_as_float(u[0].x) + __uint_as_float(u[2].x), __uint_as_float(u[0].y) + __uint_as_float(u[2].y),
                                  __uint_as_float(u[1].x) + __uint_as_float(u[3].x), __uint_as_float(u[1].y) + __uint_as_float(u[3].y)};
#pragma unroll
                    for (int i = 0; i < 4; i++) { v[i] += __shfl_xor_sync(~0u, v[i], 1); v[i] += __shfl_xor_sync(~0u, v[i], 2); }
                    ln_coeffs(v[0] * (1.f / DM), v[1] * (1.f / DM), ra2, na2);
                    ln_coeffs(v[2] * (1.f / DM), v[3] * (1.f / DM), rb2, nb2);
                }
                const uint32_t ha = sb + OFF_Y + w * HALF + (lane >> 4) * 1024 + (2 * wi + ((lane >> 3) & 1)) * 128 + (lane & 7) * 16;
                const uint32_t sta = sb + M_ST + q * 16;
                const uint32_t* xg = act + RB_X1 + tile * 14336 + (lane >> 4) * 256 + wi * 64 + (lane & 15) * 4;
                uint32_t x[8];
                const uint32_t xs = sb + OFF_Y + w * HALF + (lane >> 4) * 1024 + wi * 256 + (lane & 15) * 16;
                uint4 st[2];
                auto load = [&](int s) {
                    if (s == 4) mbar_wait_c(BAR(B_XFULL + 4 + w), 1);
                    ldsm4(ha + s * 4096, x); ldsm4(ha + s * 4096 + 2048, x + 4);
                    st[0] = lds4(sta + s * 128); st[1] = lds4(sta + s * 128 + 64);
                };
                auto prep = [&](int s, uint32_t* f) {
                    if (__any_sync(~0u, min(min(min(x[0], x[1]), min(x[2], x[3])), min(min(x[4], x[5]), min(x[6], x[7]))) < 1u - sc)) {
                        WG_WAIT(0);
                        x1_fix(xg, xs, s);
                        ldsm4(ha + s * 4096, x); ldsm4(ha + s * 4096 + 2048, x + 4);
                    }
#pragma unroll
                    for (int i = 0; i < 2; i++) {
                        f[4 * i] = hfma2(hfma2(x[4 * i], ra2, na2), st[i].x, st[i].y); f[4 * i + 1] = hfma2(hfma2(x[4 * i + 1], rb2, nb2), st[i].x, st[i].y);
                        f[4 * i + 2] = hfma2(hfma2(x[4 * i + 2], ra2, na2), st[i].z, st[i].w); f[4 * i + 3] = hfma2(hfma2(x[4 * i + 3], rb2, nb2), st[i].z, st[i].w);
                    }
                    if (s < 13) load(s + 1);
                    stsm4(ha + s * 4096, f[0], f[1], f[2], f[3]); stsm4(ha + s * 4096 + 2048, f[4], f[5], f[6], f[7]);
                };
                float ac[128];
                uint32_t fr[3][8];
                uint64_t bd = (DB128 & ~0xFFFFFFFFull) | mkdesc(sb, DB128);
                reg_def<128>(ac);
                load(0);
                prep(0, fr[0]);
                PROFC(17);
#pragma unroll
                for (int s = 0; s < 14; s++) {
                    const uint32_t* f = fr[s % 3];
                    WAIT(B_FULL + g1_slot(s), s >= 7);
                    WG_FENCE();
                    wgmma_rl_256(ac, f[0], f[1], f[2], f[3], bd, s != 0);
                    wgmma_rl_256(ac, f[4], f[5], f[6], f[7], bd + 128, 1);
                    bd += s == 6 ? p.zero - 6 * 1024ull : 1024;
                    WG_COMMIT();
                    if (s < 13) prep(s + 1, fr[(s + 1) % 3]);
                    if (s > 0) { WG_WAIT(1); warp_arrive(BAR(B_EMPTY + g1_slot(s - 1))); }
                }
                fence_async_smem();
                PROFC(18);
                WG_WAIT(0);
                reg_fence<128>(ac);
                warp_arrive(BAR(B_EMPTY + 6));
#pragma unroll
                for (int g = 0; g < 16; g++) {
                    h2a[2 * g] = hmul2(pack2_relu(ac[4 * g], ac[4 * g + 1]), pack2(ac[64 + 4 * g], ac[64 + 4 * g + 1]));
                    h2a[2 * g + 1] = hmul2(pack2_relu(ac[4 * g + 2], ac[4 * g + 3]), pack2(ac[64 + 4 * g + 2], ac[64 + 4 * g + 3]));
                }
                bar_sync(1 + w, 128);
            } else reg_def<32>(h2a);
            PROFC(19);
            if (RUN(5)) {
                float ac[64];
                reg_def<64>(ac);
                const uint32_t bx = mkdesc(sb, dconst(8192, 1024, 1));
#pragma unroll kB
                for (int s = 0; s < 7; s++) {
                    WAIT(B_FULL + s, 0);
                    const uint32_t ad = a0 + s * 512, bd = bx + (slot_off(s) >> 4);
                    WG_FENCE();
#pragma unroll
                    for (int k = 0; k < 4; k++) wgmma_ss_128<DT, DB128>(ac, ad + k * 128, bd + k * 128, (s | k) != 0);
                    WG_COMMIT();
                    if (s == 1) {
#pragma unroll
                        for (int g = 0; g < 16; g++) { h2g[(fa / 8 + g) * 512] = h2a[2 * g]; h2g[(fa / 8 + g) * 512 + 32] = h2a[2 * g + 1]; }
                        warp_arrive(BAR(B_PUB + 6));
                    }
                    if (s > 0) { WG_WAIT(1); warp_arrive(BAR(B_EMPTY + s - 1)); }
                }
                WG_WAIT(0);
                reg_fence<64>(ac);
                warp_arrive(BAR(B_EMPTY + 6));
#pragma unroll
                for (int g = 0; g < 8; g++) {
                    h2b[2 * g] = hmul2(pack2_relu(ac[4 * g], ac[4 * g + 1]), pack2(ac[32 + 4 * g], ac[32 + 4 * g + 1]));
                    h2b[2 * g + 1] = hmul2(pack2_relu(ac[4 * g + 2], ac[4 * g + 3]), pack2(ac[32 + 4 * g + 2], ac[32 + 4 * g + 3]));
                }
            } else reg_def<16>(h2b);
            PROFC(27);
            constexpr uint64_t DAN = dconst(2048, 128, 0), DW = dconst(128, 512, 0), DC = dconst(4096, 512, 2);
            float ac[56];
            reg_def<56>(ac);
            const uint64_t wd0 = (DW & ~0xFFFFFFFFull) | mkdesc(sb + 8192, DW);
            uint32_t* hcg = act + RB_HC + (tile >> 1) * 8 * 2048 + (8 * w + 2 * wi) * 32 + lane;
            {
                float ag[32];
                reg_def<32>(ag);
                const uint32_t bx = mkdesc(sb, DC);
#pragma unroll
                for (int s = 0; s < 7; s++) {
                    WAIT(B_FULL + s, 1);
                    const uint32_t ad = a0 + p.zero + s * 512, bd = bx + s * 1024;
                    const uint32_t* hh = s < 4 ? h2a + 8 * s : h2b + 8 * (s - 4);
                    WG_FENCE();
#pragma unroll
                    for (int k = 0; k < 4; k++) wgmma_ss_64<DT, DC>(ag, ad + k * 128, bd + k * 64, (s | k) != 0);
                    if (s < 6) {
                        wgmma_rl_112(ac, hh[0], hh[1], hh[2], hh[3], wd0 + s * 1024, s != 0);
                        wgmma_rl_112(ac, hh[4], hh[5], hh[6], hh[7], wd0 + s * 1024 + 16, 1);
                    }
                    WG_COMMIT();
                    if (s == 0) {
#pragma unroll
                        for (int g = 0; g < 8; g++) { h2g[(fb / 8 + g) * 512] = h2b[2 * g]; h2g[(fb / 8 + g) * 512 + 32] = h2b[2 * g + 1]; }
                        warp_arrive(BAR(B_PUB + 7));
                    }
                    if (s > 0) { WG_WAIT(1); warp_arrive(BAR(B_EMPTY + s - 1)); }
                }
                WG_WAIT(0);
                reg_fence<32>(ag);
                __syncwarp();
                if (lane < 5) mbar_arrive(BAR(B_EMPTY + 7 + lane));
                PROFC(20);
#pragma unroll
                for (int g = 0; g < 4; g++) {
                    h2b[16 + 2 * g] = hmul2(pack2_relu(ag[4 * g], ag[4 * g + 1]), pack2(ag[16 + 4 * g], ag[16 + 4 * g + 1]));
                    h2b[16 + 2 * g + 1] = hmul2(pack2_relu(ag[4 * g + 2], ag[4 * g + 3]), pack2(ag[16 + 4 * g + 2], ag[16 + 4 * g + 3]));
                    st_relaxed(hcg + j * 2048 + g * 512, nz(h2b[16 + 2 * g])); st_relaxed(hcg + j * 2048 + g * 512 + 32, nz(h2b[16 + 2 * g + 1]));
                }
                warp_arrive(BAR(B_PUB + 8));
                WG_FENCE();
                wgmma_rl_112(ac, h2b[16], h2b[17], h2b[18], h2b[19], wd0 + 6 * 1024, 1);
                wgmma_rl_112(ac, h2b[20], h2b[21], h2b[22], h2b[23], wd0 + 6 * 1024 + 16, 1);
                WG_COMMIT();
                asm volatile("barrier.cluster.wait.aligned;" ::: "memory");
                uint32_t rb;
                asm volatile("mapa.shared::cluster.u32 %0, %1, %2;" : "=r"(rb) : "r"(BAR(B_PEER)), "r"(kh ^ 1));
                asm volatile("{\n.reg .pred p;\nelect.sync _|p, 0xffffffff;\n@p mbarrier.arrive.relaxed.cluster.shared::cluster.b64 _, [%0];\n}" ::"r"(rb) : "memory");
            }
            PROFC(21);
            uint32_t ad = mkdesc(sb + 8192 + w * 1024, DAN), bd = mkdesc(sb, DW), fb_ = BAR(B_FULL), eb_ = BAR(B_EMPTY + 6), par = 0;
#pragma unroll 1
            for (int e = 0; e < 18; e++) {
                mbar_wait_c(fb_, par);
                WG_FENCE();
                wgmma_ss_112<DAN, DW>(ac, ad, bd, 1);
                wgmma_ss_112<DAN, DW>(ac, ad + 256, bd + 16, 1);
                WG_COMMIT();
                WG_WAIT(1);
                warp_arrive(eb_);
                eb_ = fb_ + 8 * (B_EMPTY - B_FULL);
                ad += 1024; bd += 1024; fb_ += 8;
                if (e == 11) { ad -= 12 * 1024; bd -= 12 * 1024; fb_ -= 96; par = 1; }
            }
            PROFC(22);
            {
                uint32_t fc_[24];
                const uint32_t la = sb + 6 * 16384 + 8192 + (lane >> 4) * 2048 + (8 * w + 2 * wi + ((lane >> 3) & 1)) * 128 + (lane & 7) * 16;
#pragma unroll
                for (int e = 0; e < 3; e++) {
                    uint32_t* f = fc_ + 8 * e;
                    WAIT(B_FULL + 6 + e, 1);
                    ldsm4(la + e * 16384, f); ldsm4(la + e * 16384 + 4096, f + 4);
                    const uint32_t* g = hcg + (2 * (e + (e >= nq)) + kh) * 2048;
                    while (__any_sync(~0u, min(min(min(f[0], f[1]), min(f[2], f[3])), min(min(f[4], f[5]), min(f[6], f[7]))) == 0u)) {
#pragma unroll
                        for (int i = 0; i < 8; i++) f[i] = ld_relaxed(g + (i >> 1) * 512 + (i & 1) * 32);
                    }
                    WG_FENCE();
                    wgmma_rl_112(ac, f[0], f[1], f[2], f[3], wd0 - 512 + (6 + e) * 1024, 1);
                    wgmma_rl_112(ac, f[4], f[5], f[6], f[7], wd0 - 512 + (6 + e) * 1024 + 16, 1);
                    WG_COMMIT();
                }
            }
            mbar_wait_cluster(BAR(B_PEER), sc);
            WG_WAIT(0);
            reg_fence<56>(ac);
            PROFC(24);
            uint32_t rdst, rbar;
            asm volatile("mapa.shared::cluster.u32 %0, %1, %2;" : "=r"(rdst) : "r"(sb + OFF_Y + (5 + w) * 16384 + t * 16), "r"(kh ^ 1 ^ sc));
            asm volatile("mapa.shared::cluster.u32 %0, %1, %2;" : "=r"(rbar) : "r"(BAR(B_XCH + w)), "r"(kh ^ 1 ^ sc));
#pragma unroll
            for (int g = 0; g < 7; g++) {
                const float v0 = ac[28 + 4 * g + 0], v1 = ac[28 + 4 * g + 1];
                const float v2 = ac[28 + 4 * g + 2], v3 = ac[28 + 4 * g + 3];
                if (!sc) asm volatile("st.async.shared::cluster.mbarrier::complete_tx::bytes.v4.f32 [%0], {%1,%2,%3,%4}, [%5];"
                             ::"r"(rdst + g * 2048), "f"(v0), "f"(v1), "f"(v2), "f"(v3), "r"(rbar) : "memory");
            }
            mbar_wait_cluster(BAR(B_XCH + w), sc);
            PROFC(25);
            bf16* og = (sc ? (bf16*)act : p.out + (size_t)128 * r * DM) + (size_t)ra * DM + 56 * j + 2 * q;
#pragma unroll
            for (int g = 0; g < 7; g++) {
                const uint4 rv = *(const uint4*)(smem + OFF_Y + (5 + w) * 16384 + t * 16 + g * 2048);
                const float2 gb = *(const float2*)(smem + M_G + 224 + (8 * g + 2 * q) * 4);
                const float v0 = ac[4 * g + 0] + __uint_as_float(rv.x), v1 = ac[4 * g + 1] + __uint_as_float(rv.y);
                const float v2 = ac[4 * g + 2] + __uint_as_float(rv.z), v3 = ac[4 * g + 3] + __uint_as_float(rv.w);
                *(uint32_t*)(og + 8 * g) = pack2(fmaf(gb.x, v0, bf_lo(x1p[2 * g])), fmaf(gb.y, v1, bf_hi(x1p[2 * g])));
                *(uint32_t*)(og + 8 * DM + 8 * g) = pack2(fmaf(gb.x, v2, bf_lo(x1p[2 * g + 1])), fmaf(gb.y, v3, bf_hi(x1p[2 * g + 1])));
            }
        }
        PROFC(26);
        bar_sync(1 + w, 128);
        if (wi == 0) warp_arrive(BAR(B_DONE));
        return;
    }
    helper_late(p, r, j, warp PROF_ARGS);
}

#undef act
typedef CUresult (*EncodeFn)(CUtensorMap*, CUtensorMapDataType, cuuint32_t, void*, const cuuint64_t*, const cuuint64_t*, const cuuint32_t*,
                             const cuuint32_t*, CUtensorMapInterleave, CUtensorMapSwizzle, CUtensorMapL2promotion, CUtensorMapFloatOOBfill);

static void make_map(EncodeFn fn, CUtensorMap* m, const void* ptr, uint64_t d0, uint64_t d1, uint64_t d2, uint64_t s1, uint64_t s2,
                     uint32_t b0, uint32_t b1, uint32_t b2, CUtensorMapSwizzle sw) {
    cuuint64_t dims[3] = {d0, d1, d2}, strides[2] = {s1, s2};
    cuuint32_t box[3] = {b0, b1, b2}, es[3] = {1, 1, 1};
    CUresult rc = fn(m, CU_TENSOR_MAP_DATA_TYPE_BFLOAT16, 3, (void*)ptr, dims, strides, box, es, CU_TENSOR_MAP_INTERLEAVE_NONE, sw,
                     CU_TENSOR_MAP_L2_PROMOTION_L2_128B, CU_TENSOR_MAP_FLOAT_OOB_FILL_NONE);
    (void)rc;
}

extern "C" void kernel_launch(void* const* d_in, const int* in_sizes, int n_in, void* d_out, int out_size) {
    (void)in_sizes; (void)n_in; (void)out_size;
    static EncodeFn fn = nullptr;
    static uint32_t* act_base = nullptr;
    if (!fn) {
        cudaDriverEntryPointQueryResult st;
        cudaGetDriverEntryPoint("cuTensorMapEncodeTiled", (void**)&fn, cudaEnableDefault, &st);
        void* a = nullptr;
        cudaGetSymbolAddress(&a, g_act);
        act_base = (uint32_t*)a;
        cudaFuncSetAttribute(fused_block_kernel, cudaFuncAttributeMaxDynamicSharedMemorySize, SMEM_BYTES);
    }
    Params p;
    p.x = (const bf16*)d_in[0];
    const bf16* wqkv = (const bf16*)d_in[1];
    p.wqkv = wqkv;
    p.wop = (const bf16*)d_in[2];
    p.wg = (const bf16*)d_in[4];
    p.wu = (const bf16*)d_in[5];
    p.wd = (const bf16*)d_in[6];
    p.c = (const bf16*)d_in[7];
    p.wmod = (const bf16*)d_in[8];
    p.out = (bf16*)d_out;
    p.zero = 0;
    p.actb = act_base;
    make_map(fn, &p.wm, p.wmod, 2688, 448, 1, 5376, 5376 * 448, 16, 224, 1, CU_TENSOR_MAP_SWIZZLE_NONE);
    make_map(fn, &p.xm, p.x, 448, 2048, 1, 896, 896 * 2048, 64, 128, 1, CU_TENSOR_MAP_SWIZZLE_128B);
    make_map(fn, &p.qkv, wqkv, 1344, 448, 1, 2688, 2688 * 448, 64, 224, 1, CU_TENSOR_MAP_SWIZZLE_128B);
    make_map(fn, &p.wo, p.wop, 448, 448, 1, 896, 896 * 448, 64, 224, 1, CU_TENSOR_MAP_SWIZZLE_128B);
    make_map(fn, &p.ga, p.wg, 64, 448, 28, 3584, 128, 64, 32, 2, CU_TENSOR_MAP_SWIZZLE_128B);
    make_map(fn, &p.ua, p.wu, 64, 448, 28, 3584, 128, 64, 32, 2, CU_TENSOR_MAP_SWIZZLE_128B);
    make_map(fn, &p.gb, p.wg, 64, 448, 28, 3584, 128, 64, 64, 1, CU_TENSOR_MAP_SWIZZLE_128B);
    make_map(fn, &p.ub, p.wu, 64, 448, 28, 3584, 128, 64, 64, 1, CU_TENSOR_MAP_SWIZZLE_128B);
    make_map(fn, &p.gc, p.wg, 32, 448, 56, 3584, 64, 32, 64, 1, CU_TENSOR_MAP_SWIZZLE_64B);
    make_map(fn, &p.uc, p.wu, 32, 448, 56, 3584, 64, 32, 64, 1, CU_TENSOR_MAP_SWIZZLE_64B);
    make_map(fn, &p.dn, p.wd, 8, 1792, 56, 896, 16, 8, 32, 7, CU_TENSOR_MAP_SWIZZLE_NONE);
    fused_block_kernel<<<GRID, 384, SMEM_BYTES>>>(p);
}
```

```cpp
#include <cuda_runtime.h>
#include <cuda_bf16.h>
#include <cuda.h>
#include <stdint.h>

typedef __nv_bfloat16 bf16;

__device__ __forceinline__ void wgmma_rl_56(float* d, uint32_t a0, uint32_t a1, uint32_t a2, uint32_t a3, uint64_t db, int sd) {
  asm volatile("{\n.reg .pred p;\nsetp.ne.b32 p, %33, 0;\n"
    "wgmma.mma_async.sync.aligned.m64n56k16.f32.bf16.bf16 {%0,%1,%2,%3,%4,%5,%6,%7,%8,%9,%10,%11,%12,%13,%14,%15,%16,%17,%18,%19,%20,%21,%22,%23,%24,%25,%26,%27}, {%28,%29,%30,%31}, %32, p, 1, 1, 1;\n}\n"
    : "+f"(d[0]),"+f"(d[1]),"+f"(d[2]),"+f"(d[3]),"+f"(d[4]),"+f"(d[5]),"+f"(d[6]),"+f"(d[7]),"+f"(d[8]),"+f"(d[9]),"+f"(d[10]),"+f"(d[11]),"+f"(d[12]),"+f"(d[13]),"+f"(d[14]),"+f"(d[15]),"+f"(d[16]),"+f"(d[17]),"+f"(d[18]),"+f"(d[19]),"+f"(d[20]),"+f"(d[21]),"+f"(d[22]),"+f"(d[23]),"+f"(d[24]),"+f"(d[25]),"+f"(d[26]),"+f"(d[27])
    : "r"(a0), "r"(a1), "r"(a2), "r"(a3), "l"(db), "r"(sd));
}
template<uint64_t CA, uint64_t CB> __device__ __forceinline__ void wgmma_ss_56(float* d, uint32_t da, uint32_t db, int sd) {
  asm volatile("{\n.reg .pred p;\n.reg .b64 a, b;\nsetp.ne.b32 p, %30, 0;\nmov.b64 a, {%28, %31};\nmov.b64 b, {%29, %32};\n"
    "wgmma.mma_async.sync.aligned.m64n56k16.f32.bf16.bf16 {%0,%1,%2,%3,%4,%5,%6,%7,%8,%9,%10,%11,%12,%13,%14,%15,%16,%17,%18,%19,%20,%21,%22,%23,%24,%25,%26,%27}, a, b, p, 1, 1, 0, 1;\n}\n"
    : "+f"(d[0]),"+f"(d[1]),"+f"(d[2]),"+f"(d[3]),"+f"(d[4]),"+f"(d[5]),"+f"(d[6]),"+f"(d[7]),"+f"(d[8]),"+f"(d[9]),"+f"(d[10]),"+f"(d[11]),"+f"(d[12]),"+f"(d[13]),"+f"(d[14]),"+f"(d[15]),"+f"(d[16]),"+f"(d[17]),"+f"(d[18]),"+f"(d[19]),"+f"(d[20]),"+f"(d[21]),"+f"(d[22]),"+f"(d[23]),"+f"(d[24]),"+f"(d[25]),"+f"(d[26]),"+f"(d[27])
    : "r"(da), "r"(db), "r"(sd), "n"((uint32_t)(CA >> 32)), "n"((uint32_t)(CB >> 32)));
}
__device__ __forceinline__ void wgmma_rl_256(float* d, uint32_t a0, uint32_t a1, uint32_t a2, uint32_t a3, uint64_t db, int sd) {
  asm volatile("{\n.reg .pred p;\nsetp.ne.b32 p, %133, 0;\n"
    "wgmma.mma_async.sync.aligned.m64n256k16.f32.bf16.bf16 {%0,%1,%2,%3,%4,%5,%6,%7,%8,%9,%10,%11,%12,%13,%14,%15,%16,%17,%18,%19,%20,%21,%22,%23,%24,%25,%26,%27,%28,%29,%30,%31,%32,%33,%34,%35,%36,%37,%38,%39,%40,%41,%42,%43,%44,%45,%46,%47,%48,%49,%50,%51,%52,%53,%54,%55,%56,%57,%58,%59,%60,%61,%62,%63,%64,%65,%66,%67,%68,%69,%70,%71,%72,%73,%74,%75,%76,%77,%78,%79,%80,%81,%82,%83,%84,%85,%86,%87,%88,%89,%90,%91,%92,%93,%94,%95,%96,%97,%98,%99,%100,%101,%102,%103,%104,%105,%106,%107,%108,%109,%110,%111,%112,%113,%114,%115,%116,%117,%118,%119,%120,%121,%122,%123,%124,%125,%126,%127}, {%128,%129,%130,%131}, %132, p, 1, 1, 1;\n}\n"
    : "+f"(d[0]),"+f"(d[1]),"+f"(d[2]),"+f"(d[3]),"+f"(d[4]),"+f"(d[5]),"+f"(d[6]),"+f"(d[7]),"+f"(d[8]),"+f"(d[9]),"+f"(d[10]),"+f"(d[11]),"+f"(d[12]),"+f"(d[13]),"+f"(d[14]),"+f"(d[15]),"+f"(d[16]),"+f"(d[17]),"+f"(d[18]),"+f"(d[19]),"+f"(d[20]),"+f"(d[21]),"+f"(d[22]),"+f"(d[23]),"+f"(d[24]),"+f"(d[25]),"+f"(d[26]),"+f"(d[27]),"+f"(d[28]),"+f"(d[29]),"+f"(d[30]),"+f"(d[31]),"+f"(d[32]),"+f"(d[33]),"+f"(d[34]),"+f"(d[35]),"+f"(d[36]),"+f"(d[37]),"+f"(d[38]),"+f"(d[39]),"+f"(d[40]),"+f"(d[41]),"+f"(d[42]),"+f"(d[43]),"+f"(d[44]),"+f"(d[45]),"+f"(d[46]),"+f"(d[47]),"+f"(d[48]),"+f"(d[49]),"+f"(d[50]),"+f"(d[51]),"+f"(d[52]),"+f"(d[53]),"+f"(d[54]),"+f"(d[55]),"+f"(d[56]),"+f"(d[57]),"+f"(d[58]),"+f"(d[59]),"+f"(d[60]),"+f"(d[61]),"+f"(d[62]),"+f"(d[63]),"+f"(d[64]),"+f"(d[65]),"+f"(d[66]),"+f"(d[67]),"+f"(d[68]),"+f"(d[69]),"+f"(d[70]),"+f"(d[71]),"+f"(d[72]),"+f"(d[73]),"+f"(d[74]),"+f"(d[75]),"+f"(d[76]),"+f"(d[77]),"+f"(d[78]),"+f"(d[79]),"+f"(d[80]),"+f"(d[81]),"+f"(d[82]),"+f"(d[83]),"+f"(d[84]),"+f"(d[85]),"+f"(d[86]),"+f"(d[87]),"+f"(d[88]),"+f"(d[89]),"+f"(d[90]),"+f"(d[91]),"+f"(d[92]),"+f"(d[93]),"+f"(d[94]),"+f"(d[95]),"+f"(d[96]),"+f"(d[97]),"+f"(d[98]),"+f"(d[99]),"+f"(d[100]),"+f"(d[101]),"+f"(d[102]),"+f"(d[103]),"+f"(d[104]),"+f"(d[105]),"+f"(d[106]),"+f"(d[107]),"+f"(d[108]),"+f"(d[109]),"+f"(d[110]),"+f"(d[111]),"+f"(d[112]),"+f"(d[113]),"+f"(d[114]),"+f"(d[115]),"+f"(d[116]),"+f"(d[117]),"+f"(d[118]),"+f"(d[119]),"+f"(d[120]),"+f"(d[121]),"+f"(d[122]),"+f"(d[123]),"+f"(d[124]),"+f"(d[125]),"+f"(d[126]),"+f"(d[127])
    : "r"(a0), "r"(a1), "r"(a2), "r"(a3), "l"(db), "r"(sd));
}
template<uint64_t CA, uint64_t CB> __device__ __forceinline__ void wgmma_ss_128(float* d, uint32_t da, uint32_t db, int sd) {
  asm volatile("{\n.reg .pred p;\n.reg .b64 a, b;\nsetp.ne.b32 p, %66, 0;\nmov.b64 a, {%64, %67};\nmov.b64 b, {%65, %68};\n"
    "wgmma.mma_async.sync.aligned.m64n128k16.f32.bf16.bf16 {%0,%1,%2,%3,%4,%5,%6,%7,%8,%9,%10,%11,%12,%13,%14,%15,%16,%17,%18,%19,%20,%21,%22,%23,%24,%25,%26,%27,%28,%29,%30,%31,%32,%33,%34,%35,%36,%37,%38,%39,%40,%41,%42,%43,%44,%45,%46,%47,%48,%49,%50,%51,%52,%53,%54,%55,%56,%57,%58,%59,%60,%61,%62,%63}, a, b, p, 1, 1, 0, 1;\n}\n"
    : "+f"(d[0]),"+f"(d[1]),"+f"(d[2]),"+f"(d[3]),"+f"(d[4]),"+f"(d[5]),"+f"(d[6]),"+f"(d[7]),"+f"(d[8]),"+f"(d[9]),"+f"(d[10]),"+f"(d[11]),"+f"(d[12]),"+f"(d[13]),"+f"(d[14]),"+f"(d[15]),"+f"(d[16]),"+f"(d[17]),"+f"(d[18]),"+f"(d[19]),"+f"(d[20]),"+f"(d[21]),"+f"(d[22]),"+f"(d[23]),"+f"(d[24]),"+f"(d[25]),"+f"(d[26]),"+f"(d[27]),"+f"(d[28]),"+f"(d[29]),"+f"(d[30]),"+f"(d[31]),"+f"(d[32]),"+f"(d[33]),"+f"(d[34]),"+f"(d[35]),"+f"(d[36]),"+f"(d[37]),"+f"(d[38]),"+f"(d[39]),"+f"(d[40]),"+f"(d[41]),"+f"(d[42]),"+f"(d[43]),"+f"(d[44]),"+f"(d[45]),"+f"(d[46]),"+f"(d[47]),"+f"(d[48]),"+f"(d[49]),"+f"(d[50]),"+f"(d[51]),"+f"(d[52]),"+f"(d[53]),"+f"(d[54]),"+f"(d[55]),"+f"(d[56]),"+f"(d[57]),"+f"(d[58]),"+f"(d[59]),"+f"(d[60]),"+f"(d[61]),"+f"(d[62]),"+f"(d[63])
    : "r"(da), "r"(db), "r"(sd), "n"((uint32_t)(CA >> 32)), "n"((uint32_t)(CB >> 32)));
}
template<uint64_t CA, uint64_t CB> __device__ __forceinline__ void wgmma_ss_64(float* d, uint32_t da, uint32_t db, int sd) {
  asm volatile("{\n.reg .pred p;\n.reg .b64 a, b;\nsetp.ne.b32 p, %34, 0;\nmov.b64 a, {%32, %35};\nmov.b64 b, {%33, %36};\n"
    "wgmma.mma_async.sync.aligned.m64n64k16.f32.bf16.bf16 {%0,%1,%2,%3,%4,%5,%6,%7,%8,%9,%10,%11,%12,%13,%14,%15,%16,%17,%18,%19,%20,%21,%22,%23,%24,%25,%26,%27,%28,%29,%30,%31}, a, b, p, 1, 1, 0, 1;\n}\n"
    : "+f"(d[0]),"+f"(d[1]),"+f"(d[2]),"+f"(d[3]),"+f"(d[4]),"+f"(d[5]),"+f"(d[6]),"+f"(d[7]),"+f"(d[8]),"+f"(d[9]),"+f"(d[10]),"+f"(d[11]),"+f"(d[12]),"+f"(d[13]),"+f"(d[14]),"+f"(d[15]),"+f"(d[16]),"+f"(d[17]),"+f"(d[18]),"+f"(d[19]),"+f"(d[20]),"+f"(d[21]),"+f"(d[22]),"+f"(d[23]),"+f"(d[24]),"+f"(d[25]),"+f"(d[26]),"+f"(d[27]),"+f"(d[28]),"+f"(d[29]),"+f"(d[30]),"+f"(d[31])
    : "r"(da), "r"(db), "r"(sd), "n"((uint32_t)(CA >> 32)), "n"((uint32_t)(CB >> 32)));
}
template<uint64_t CA, uint64_t CB> __device__ __forceinline__ void wgmma_ss_112(float* d, uint32_t da, uint32_t db, int sd) {
  asm volatile("{\n.reg .pred p;\n.reg .b64 a, b;\nsetp.ne.b32 p, %58, 0;\nmov.b64 a, {%56, %59};\nmov.b64 b, {%57, %60};\n"
    "wgmma.mma_async.sync.aligned.m64n112k16.f32.bf16.bf16 {%0,%1,%2,%3,%4,%5,%6,%7,%8,%9,%10,%11,%12,%13,%14,%15,%16,%17,%18,%19,%20,%21,%22,%23,%24,%25,%26,%27,%28,%29,%30,%31,%32,%33,%34,%35,%36,%37,%38,%39,%40,%41,%42,%43,%44,%45,%46,%47,%48,%49,%50,%51,%52,%53,%54,%55}, a, b, p, 1, 1, 0, 1;\n}\n"
    : "+f"(d[0]),"+f"(d[1]),"+f"(d[2]),"+f"(d[3]),"+f"(d[4]),"+f"(d[5]),"+f"(d[6]),"+f"(d[7]),"+f"(d[8]),"+f"(d[9]),"+f"(d[10]),"+f"(d[11]),"+f"(d[12]),"+f"(d[13]),"+f"(d[14]),"+f"(d[15]),"+f"(d[16]),"+f"(d[17]),"+f"(d[18]),"+f"(d[19]),"+f"(d[20]),"+f"(d[21]),"+f"(d[22]),"+f"(d[23]),"+f"(d[24]),"+f"(d[25]),"+f"(d[26]),"+f"(d[27]),"+f"(d[28]),"+f"(d[29]),"+f"(d[30]),"+f"(d[31]),"+f"(d[32]),"+f"(d[33]),"+f"(d[34]),"+f"(d[35]),"+f"(d[36]),"+f"(d[37]),"+f"(d[38]),"+f"(d[39]),"+f"(d[40]),"+f"(d[41]),"+f"(d[42]),"+f"(d[43]),"+f"(d[44]),"+f"(d[45]),"+f"(d[46]),"+f"(d[47]),"+f"(d[48]),"+f"(d[49]),"+f"(d[50]),"+f"(d[51]),"+f"(d[52]),"+f"(d[53]),"+f"(d[54]),"+f"(d[55])
    : "r"(da), "r"(db), "r"(sd), "n"((uint32_t)(CA >> 32)), "n"((uint32_t)(CB >> 32)));
}
__device__ __forceinline__ void wgmma_rl_112(float* d, uint32_t a0, uint32_t a1, uint32_t a2, uint32_t a3, uint64_t db, int sd) {
  asm volatile("{\n.reg .pred p;\nsetp.ne.b32 p, %61, 0;\n"
    "wgmma.mma_async.sync.aligned.m64n112k16.f32.bf16.bf16 {%0,%1,%2,%3,%4,%5,%6,%7,%8,%9,%10,%11,%12,%13,%14,%15,%16,%17,%18,%19,%20,%21,%22,%23,%24,%25,%26,%27,%28,%29,%30,%31,%32,%33,%34,%35,%36,%37,%38,%39,%40,%41,%42,%43,%44,%45,%46,%47,%48,%49,%50,%51,%52,%53,%54,%55}, {%56,%57,%58,%59}, %60, p, 1, 1, 1;\n}\n"
    : "+f"(d[0]),"+f"(d[1]),"+f"(d[2]),"+f"(d[3]),"+f"(d[4]),"+f"(d[5]),"+f"(d[6]),"+f"(d[7]),"+f"(d[8]),"+f"(d[9]),"+f"(d[10]),"+f"(d[11]),"+f"(d[12]),"+f"(d[13]),"+f"(d[14]),"+f"(d[15]),"+f"(d[16]),"+f"(d[17]),"+f"(d[18]),"+f"(d[19]),"+f"(d[20]),"+f"(d[21]),"+f"(d[22]),"+f"(d[23]),"+f"(d[24]),"+f"(d[25]),"+f"(d[26]),"+f"(d[27]),"+f"(d[28]),"+f"(d[29]),"+f"(d[30]),"+f"(d[31]),"+f"(d[32]),"+f"(d[33]),"+f"(d[34]),"+f"(d[35]),"+f"(d[36]),"+f"(d[37]),"+f"(d[38]),"+f"(d[39]),"+f"(d[40]),"+f"(d[41]),"+f"(d[42]),"+f"(d[43]),"+f"(d[44]),"+f"(d[45]),"+f"(d[46]),"+f"(d[47]),"+f"(d[48]),"+f"(d[49]),"+f"(d[50]),"+f"(d[51]),"+f"(d[52]),"+f"(d[53]),"+f"(d[54]),"+f"(d[55])
    : "r"(a0), "r"(a1), "r"(a2), "r"(a3), "l"(db), "r"(sd));
}

constexpr int DM = 448;
constexpr int NCTA = 128;
#define MAPPING 1
#define GRID 128
#define PINGPONG 0
#define WIN 6
#define WIN_END 25
#define UNR_B 1
#define UNR_C 1
constexpr int kB = UNR_B, kC = UNR_C;
#define LIKELY(x) __builtin_expect(!!(x), 1)
#define PACE 1
#define PACE_END 6
#define GEMV_AT 1
#define NPRE 14
#define MAP_S 4
constexpr int SPIN_LIMIT = 1 << 22;

constexpr uint32_t OFF_X = 0, OFF_Y = 114688, OFF_MISC = 229376, SMEM_BYTES = 232448;
constexpr uint32_t Y_VR = 0, Y_K = 28672, Y_KOWN = 57344, Y_VOWN = 71680, Y_Q = 86016;
constexpr uint32_t HALF = 57344;
constexpr uint32_t X_STAT = 49152;
constexpr uint32_t OUT_STAGE = 16384;
constexpr uint32_t M_BAR = OFF_MISC;
constexpr uint32_t M_ST = OFF_MISC + 512;
constexpr uint32_t M_G = OFF_MISC + 2304;
constexpr uint32_t M_EPOCH = OFF_MISC + 3040;
enum { B_XFULL = 0, B_FULLK = 7, B_FULLV = 8, B_FULLQ, B_KRFULL, B_VRFULL, B_WOFULL, B_XCH, B_MOD1 = 15, B_FULL = 16, B_WMFULL = 30,
       B_EMPTY = 32, B_XFREE = B_EMPTY + 12, B_GEMV, B_PEER,
       B_PUB = 47,
       B_WMFREE = 56, B_HRDY, B_GFULL = B_HRDY + 3, B_DONE = 31, B_DUMMY = B_GEMV };

__device__ uint32_t g_ticket;
__device__ __align__(128) uint32_t g_mod[8 * 6 * DM];
__device__ __align__(128) uint32_t g_flag[144 * 128];
constexpr int RB_WORDS = 262144, RB_KV = 0, RB_O = 57344, RB_X1 = 86016, RB_H2 = 143360, RB_ST = 258048;
__device__ __align__(128) uint32_t g_act[18 * RB_WORDS];
__device__ __align__(128) uint32_t g_wd[56 * 4 * 1792];
#define PROFH(id)
#define PROFH1(id)
#define PROFC(id)

struct alignas(64) Params {
    CUtensorMap wm, wm2, om, xm, qkv, wo, ga, ua, gb, ub, gc, uc, dn;
    const bf16 *x, *c, *wqkv, *wmod, *wg, *wu, *wd, *wop;
    bf16* out;
    uint32_t* actb;
    uint32_t zero;
};

__device__ __forceinline__ void mbar_init(uint32_t bar, int cnt) { asm volatile("mbarrier.init.shared::cta.b64 [%0], %1;" ::"r"(bar), "r"(cnt) : "memory"); }
__device__ __forceinline__ void mbar_expect_tx(uint32_t bar, uint32_t bytes) { asm volatile("mbarrier.arrive.expect_tx.shared::cta.b64 _, [%0], %1;" ::"r"(bar), "r"(bytes) : "memory"); }
__device__ __forceinline__ void mbar_arrive(uint32_t bar) { asm volatile("mbarrier.arrive.shared::cta.b64 _, [%0];" ::"r"(bar) : "memory"); }
__device__ __forceinline__ void mbar_wait(uint32_t bar, uint32_t parity) {
    uint32_t ok; int n = 0;
    do {
        asm volatile("{\n.reg .pred p;\nmbarrier.try_wait.parity.shared::cta.b64 p, [%1], %2;\nselp.u32 %0, 1, 0, p;\n}" : "=r"(ok) : "r"(bar), "r"(parity) : "memory");
        if (++n > SPIN_LIMIT) __trap();
    } while (!ok);
}
__device__ __forceinline__ void mbar_wait_c(uint32_t bar, uint32_t parity) {
    asm volatile("{\n.reg .pred p;\nWL:\nmbarrier.try_wait.parity.shared::cta.b64 p, [%0], %1, 0x989680;\n@!p bra WL;\n}" ::"r"(bar), "r"(parity) : "memory");
}
__device__ __forceinline__ void mbar_wait_cluster(uint32_t bar, uint32_t parity) {
    asm volatile("{\n.reg .pred p;\nWL:\nmbarrier.try_wait.parity.acquire.cluster.shared::cta.b64 p, [%0], %1, 0x989680;\n@!p bra WL;\n}" ::"r"(bar), "r"(parity) : "memory");
}
__device__ __forceinline__ void warp_arrive(uint32_t bar) {
    __syncwarp();
    asm volatile("{\n.reg .pred p;\nelect.sync _|p, 0xffffffff;\n@p mbarrier.arrive.shared::cta.b64 _, [%0];\n}" ::"r"(bar) : "memory");
}
__device__ __forceinline__ int opaque(int v) { return __shfl_sync(~0u, v, 0); }
__device__ __forceinline__ int fresh_tid() { int v; asm volatile("mov.u32 %0, %%tid.x;" : "=r"(v)); return v; }
__device__ __forceinline__ void bar_sync(int id, int n) { asm volatile("bar.sync %0, %1;" ::"r"(id), "r"(n) : "memory"); }
__device__ __forceinline__ void bar_arrive(int id, int n) { asm volatile("bar.arrive %0, %1;" ::"r"(id), "r"(n) : "memory"); }
__device__ __forceinline__ void fence_async_smem() { asm volatile("fence.proxy.async.shared::cta;" ::: "memory"); }
__device__ __forceinline__ void fence_async_global() { asm volatile("fence.proxy.async.global;" ::: "memory"); }
__device__ __forceinline__ void fence_gpu() { asm volatile("fence.release.gpu;" ::: "memory"); }
__device__ __forceinline__ void tma3(uint32_t dst, const CUtensorMap* m, int c0, int c1, int c2, uint32_t bar) {
    asm volatile("cp.async.bulk.tensor.3d.shared::cluster.global.mbarrier::complete_tx::bytes [%0], [%1, {%3, %4, %5}], [%2];"
                 ::"r"(dst), "l"(m), "r"(bar), "r"(c0), "r"(c1), "r"(c2) : "memory");
}
__device__ __forceinline__ void bulk_load(uint32_t dst, const void* src, uint32_t bytes, uint32_t bar) {
    asm volatile("cp.async.bulk.shared::cluster.global.mbarrier::complete_tx::bytes [%0], [%1], %2, [%3];" ::"r"(dst), "l"(src), "r"(bytes), "r"(bar) : "memory");
}
__device__ __forceinline__ void expect_e(uint32_t bar, uint32_t bytes) {
    asm volatile("{\n.reg .pred p;\nelect.sync _|p, 0xffffffff;\n@p mbarrier.arrive.expect_tx.shared::cta.b64 _, [%0], %1;\n}" ::"r"(bar), "r"(bytes) : "memory");
}
__device__ __forceinline__ void tma3_e(uint32_t dst, const CUtensorMap* m, int c0, int c1, int c2, uint32_t bar) {
    asm volatile("{\n.reg .pred p;\nelect.sync _|p, 0xffffffff;\n@p cp.async.bulk.tensor.3d.shared::cluster.global.mbarrier::complete_tx::bytes [%0], [%1, {%3, %4, %5}], [%2];\n}"
                 ::"r"(dst), "l"(m), "r"(bar), "r"(c0), "r"(c1), "r"(c2) : "memory");
}
__device__ __forceinline__ void bulk_e(uint32_t dst, const void* src, uint32_t bytes, uint32_t bar) {
    asm volatile("{\n.reg .pred p;\nelect.sync _|p, 0xffffffff;\n@p cp.async.bulk.shared::cluster.global.mbarrier::complete_tx::bytes [%0], [%1], %2, [%3];\n}"
                 ::"r"(dst), "l"(src), "r"(bytes), "r"(bar) : "memory");
}
__device__ __forceinline__ void init_e(uint32_t bar, int cnt) {
    asm volatile("{\n.reg .pred p;\nelect.sync _|p, 0xffffffff;\n@p mbarrier.init.shared::cta.b64 [%0], %1;\n}" ::"r"(bar), "r"(cnt) : "memory");
}
__device__ __forceinline__ void l2_prefetch_e(const void* src, uint32_t bytes) {
    asm volatile("{\n.reg .pred p;\nelect.sync _|p, 0xffffffff;\n@p cp.async.bulk.prefetch.L2.global [%0], %1;\n}" ::"l"(src), "r"(bytes) : "memory");
}
__device__ __forceinline__ uint32_t ld_relaxed(const uint32_t* p) { uint32_t v; asm volatile("ld.relaxed.gpu.global.u32 %0, [%1];" : "=r"(v) : "l"(p) : "memory"); return v; }
__device__ __forceinline__ void st_relaxed(uint32_t* p, uint32_t v) { asm volatile("st.relaxed.gpu.global.u32 [%0], %1;" ::"l"(p), "r"(v) : "memory"); }
__device__ __forceinline__ uint4 ld_relaxed4(const uint4* p) { uint4 v; asm volatile("ld.relaxed.gpu.global.v4.u32 {%0,%1,%2,%3}, [%4];" : "=r"(v.x), "=r"(v.y), "=r"(v.z), "=r"(v.w) : "l"(p) : "memory"); return v; }
__device__ __forceinline__ void st_relaxed4(uint4* p, uint4 v) { asm volatile("st.relaxed.gpu.global.v4.u32 [%0], {%1,%2,%3,%4};" ::"l"(p), "r"(v.x), "r"(v.y), "r"(v.z), "r"(v.w) : "memory"); }
__device__ __forceinline__ uint4 ldg_nc4(const void* p) { uint4 v; asm volatile("ld.global.nc.L1::no_allocate.v4.u32 {%0,%1,%2,%3}, [%4];" : "=r"(v.x), "=r"(v.y), "=r"(v.z), "=r"(v.w) : "l"(p)); return v; }
__device__ __forceinline__ uint32_t ldg_nc(const void* p) { uint32_t v; asm volatile("ld.global.nc.u32 %0, [%1];" : "=r"(v) : "l"(p)); return v; }
__device__ __forceinline__ uint32_t ld_acquire(const uint32_t* p) { uint32_t v; asm volatile("ld.acquire.gpu.global.u32 %0, [%1];" : "=r"(v) : "l"(p) : "memory"); return v; }
__device__ __forceinline__ uint4 lds4(uint32_t a) { uint4 v; asm volatile("ld.shared.v4.u32 {%0,%1,%2,%3}, [%4];" : "=r"(v.x), "=r"(v.y), "=r"(v.z), "=r"(v.w) : "r"(a) : "memory"); return v; }
__device__ __forceinline__ float2 lds2f(uint32_t a) { float2 v; asm volatile("ld.shared.v2.f32 {%0,%1}, [%2];" : "=f"(v.x), "=f"(v.y) : "r"(a) : "memory"); return v; }
__device__ __forceinline__ uint32_t lds1(uint32_t a) { uint32_t v; asm volatile("ld.shared.u32 %0, [%1];" : "=r"(v) : "r"(a) : "memory"); return v; }
__device__ __forceinline__ void sts4(uint32_t a, uint4 v) { asm volatile("st.shared.v4.u32 [%0], {%1,%2,%3,%4};" ::"r"(a), "r"(v.x), "r"(v.y), "r"(v.z), "r"(v.w) : "memory"); }
__device__ __forceinline__ void sts2(uint32_t a, uint32_t x, uint32_t y) { asm volatile("st.shared.v2.u32 [%0], {%1,%2};" ::"r"(a), "r"(x), "r"(y) : "memory"); }
__device__ __forceinline__ void sts1(uint32_t a, uint32_t v) { asm volatile("st.shared.u32 [%0], %1;" ::"r"(a), "r"(v) : "memory"); }
__device__ __forceinline__ void stsm4(uint32_t a, uint32_t r0, uint32_t r1, uint32_t r2, uint32_t r3) {
    asm volatile("stmatrix.sync.aligned.m8n8.x4.shared.b16 [%0], {%1,%2,%3,%4};" ::"r"(a), "r"(r0), "r"(r1), "r"(r2), "r"(r3));
}
__device__ __forceinline__ uint32_t pack2(float lo, float hi) { uint32_t r; asm("cvt.rn.bf16x2.f32 %0, %1, %2;" : "=r"(r) : "f"(hi), "f"(lo)); return r; }
__device__ __forceinline__ uint32_t pack2_relu(float lo, float hi) { uint32_t r; asm("cvt.rn.relu.bf16x2.f32 %0, %1, %2;" : "=r"(r) : "f"(hi), "f"(lo)); return r; }
__device__ __forceinline__ uint32_t hfma2(uint32_t a, uint32_t b, uint32_t c) { uint32_t r; asm("fma.rn.bf16x2 %0, %1, %2, %3;" : "=r"(r) : "r"(a), "r"(b), "r"(c)); return r; }
__device__ __forceinline__ uint32_t hmul2(uint32_t a, uint32_t b) { uint32_t r; asm("mul.rn.bf16x2 %0, %1, %2;" : "=r"(r) : "r"(a), "r"(b)); return r; }
__device__ __forceinline__ float bf_lo(uint32_t v) { return __uint_as_float(v << 16); }
__device__ __forceinline__ float bf_hi(uint32_t v) { return __uint_as_float(v & 0xFFFF0000u); }
__device__ __forceinline__ float bf_round(float v) { return bf_lo(pack2(v, 0.f)); }
__device__ __forceinline__ float ex2(float x) { float r; asm("ex2.approx.ftz.f32 %0, %1;" : "=f"(r) : "f"(x)); return r; }
__device__ __forceinline__ void mma16816(float* d, uint32_t a0, uint32_t a1, uint32_t a2, uint32_t a3, uint32_t b0, uint32_t b1) {
    asm("mma.sync.aligned.m16n8k16.row.col.f32.bf16.bf16.f32 {%0,%1,%2,%3}, {%4,%5,%6,%7}, {%8,%9}, {%0,%1,%2,%3};"
        : "+f"(d[0]), "+f"(d[1]), "+f"(d[2]), "+f"(d[3]) : "r"(a0), "r"(a1), "r"(a2), "r"(a3), "r"(b0), "r"(b1));
}
__device__ __forceinline__ void mma16816_first(float* d, uint32_t a0, uint32_t a1, uint32_t a2, uint32_t a3, uint32_t b0, uint32_t b1) {
    asm volatile("mma.sync.aligned.m16n8k16.row.col.f32.bf16.bf16.f32 {%0,%1,%2,%3}, {%4,%5,%6,%7}, {%8,%9}, {%10,%10,%10,%10};"
        : "=f"(d[0]), "=f"(d[1]), "=f"(d[2]), "=f"(d[3]) : "r"(a0), "r"(a1), "r"(a2), "r"(a3), "r"(b0), "r"(b1), "f"(0.f));
}
__device__ __forceinline__ void mma16816_v(float* d, uint32_t a0, uint32_t a1, uint32_t a2, uint32_t a3, uint32_t b0, uint32_t b1) {
    asm volatile("mma.sync.aligned.m16n8k16.row.col.f32.bf16.bf16.f32 {%0,%1,%2,%3}, {%4,%5,%6,%7}, {%8,%9}, {%0,%1,%2,%3};"
        : "+f"(d[0]), "+f"(d[1]), "+f"(d[2]), "+f"(d[3]) : "r"(a0), "r"(a1), "r"(a2), "r"(a3), "r"(b0), "r"(b1));
}
__device__ __forceinline__ void mma1688(float* d, uint32_t a0, uint32_t a1, uint32_t b0) {
    asm("mma.sync.aligned.m16n8k8.row.col.f32.bf16.bf16.f32 {%0,%1,%2,%3}, {%4,%5}, {%6}, {%0,%1,%2,%3};"
        : "+f"(d[0]), "+f"(d[1]), "+f"(d[2]), "+f"(d[3]) : "r"(a0), "r"(a1), "r"(b0));
}
__device__ __forceinline__ void ldsm4(uint32_t a, uint32_t* r) {
    asm volatile("ldmatrix.sync.aligned.m8n8.x4.shared.b16 {%0,%1,%2,%3}, [%4];" : "=r"(r[0]), "=r"(r[1]), "=r"(r[2]), "=r"(r[3]) : "r"(a));
}
__device__ __forceinline__ void ldsm4t(uint32_t a, uint32_t* r) {
    asm volatile("ldmatrix.sync.aligned.m8n8.x4.trans.shared.b16 {%0,%1,%2,%3}, [%4];" : "=r"(r[0]), "=r"(r[1]), "=r"(r[2]), "=r"(r[3]) : "r"(a));
}
__device__ __forceinline__ uint32_t nz(uint32_t v) { uint32_t r; asm("max.u32 %0, %1, 1;" : "=r"(r) : "r"(v)); return r; }
__device__ __forceinline__ float rcp(float x) { float r; asm("rcp.approx.ftz.f32 %0, %1;" : "=f"(r) : "f"(x)); return r; }
__device__ __forceinline__ uint2 ld_relaxed2(const void* p) { uint2 v; asm volatile("ld.relaxed.gpu.global.v2.u32 {%0,%1}, [%2];" : "=r"(v.x), "=r"(v.y) : "l"(p) : "memory"); return v; }
__device__ __forceinline__ void st_relaxed2(void* p, uint32_t x, uint32_t y) { asm volatile("st.relaxed.gpu.global.v2.u32 [%0], {%1,%2};" ::"l"(p), "r"(max(x, 1u)), "r"(max(y, 1u)) : "memory"); }
__host__ __device__ constexpr uint64_t dconst(uint32_t lbo, uint32_t sbo, uint32_t swz) {
    return ((uint64_t)(lbo >> 4) << 16) | ((uint64_t)(sbo >> 4) << 32) | ((uint64_t)swz << 62);
}
__device__ __forceinline__ uint32_t mkdesc(uint32_t addr, uint64_t c) { return (uint32_t)c | ((addr & 0x3FFFF) >> 4); }
#define WG_FENCE() asm volatile("wgmma.fence.sync.aligned;" ::: "memory")
#define WG_COMMIT() asm volatile("wgmma.commit_group.sync.aligned;" ::: "memory")
#define WG_WAIT(n) asm volatile("wgmma.wait_group.sync.aligned %0;" ::"n"(n) : "memory")
template <int N> __device__ __forceinline__ void reg_fence(float* d) {
#pragma unroll
    for (int i = 0; i < N; i++) asm volatile("" : "+f"(d[i])::"memory");
}
template <int N> __device__ __forceinline__ void reg_def(float* d) {
#pragma unroll
    for (int i = 0; i < N; i++) asm volatile("" : "=f"(d[i]));
}
template <int N> __device__ __forceinline__ void reg_def(uint32_t* d) {
#pragma unroll
    for (int i = 0; i < N; i++) asm volatile("" : "=r"(d[i]));
}
__device__ __forceinline__ bool is_unset(uint4 v) { return min(min(v.x, v.y), min(v.z, v.w)) == 0u; }
__device__ __forceinline__ uint4 nz4(uint32_t a, uint32_t b, uint32_t c, uint32_t d) { return make_uint4(max(a, 1u), max(b, 1u), max(c, 1u), max(d, 1u)); }
__device__ __forceinline__ void wait_flags(const uint32_t* p, uint32_t target, uint32_t mask) {
    int n = 0;
    while (~__ballot_sync(~0u, (int)(ld_relaxed(p) - target) >= 0) & mask) { if (++n > SPIN_LIMIT) __trap(); }
    asm volatile("fence.acquire.gpu;" ::: "memory");
}
__device__ __forceinline__ float silu_bf(uint32_t cbits) {
    const float c = __uint_as_float(cbits << 16);
    return bf_round(__fdividef(c, 1.f + fminf(ex2(-1.4426950408889634f * c), 1e30f)));
}
__device__ __forceinline__ void gemv_part(uint32_t wmbuf, int wp, int lane) {
    const uint32_t wa = wmbuf + wp * 512 + (8 * (lane >> 4) + (lane & 7)) * 32 + ((lane >> 3) & 1) * 16;
    float d[4] = {};
#pragma unroll
    for (int i = 0; i < 4; i++) {
        uint32_t A[4];
        const float2 v = lds2f(wmbuf + 28672 + (wp + 8 * i) * 32 + (lane & 3) * 8);
        ldsm4t(wa + (i < 3 || wp < 4 ? i : 0) * 4096, A);
        mma16816(d, A[0], A[1], A[2], A[3], __float_as_uint(v.x), __float_as_uint(v.y));
    }
    if ((lane & 3) == 0) {
        sts1(wmbuf + 29696 + (wp * 16 + (lane >> 2)) * 4, __float_as_uint(d[0]));
        sts1(wmbuf + 29696 + (wp * 16 + 8 + (lane >> 2)) * 4, __float_as_uint(d[2]));
    }
}
__device__ __forceinline__ uint32_t mod_word(float v, int col, uint32_t target) {
    v = bf_round(v);
    if ((col >= DM && col < 2 * DM) || (col >= 4 * DM && col < 5 * DM)) v += 1.f;
    return (pack2(v, 0.f) << 16) | (target & 0xFFFFu);
}
__device__ __forceinline__ const uint4* mod_src(int i, int r, int j, bool p2) {
    i = min(i, p2 ? 251 : 223);
    return (const uint4*)g_mod + (r & 7) * (6 * DM / 4) + (i < 224 ? (p2 ? 336 : 0) + i : (i < 238 ? 14 * j + i : 14 * j + i + 322));
}
__device__ __forceinline__ void mod_store(uint32_t sb, uint4 v, const uint4* src, int i) {
    const uint32_t tag = lds1(sb + M_EPOCH) + 1;
    while (__any_sync(~0u, (((v.x ^ tag) | (v.y ^ tag) | (v.z ^ tag) | (v.w ^ tag)) & 0xFFFFu) != 0u)) v = ld_relaxed4(src);
    if (i < 224) {
        const int isc = i >= 112, c4 = i - 112 * isc;
        const uint32_t a = sb + M_ST + (c4 >> 2) * 64 + (c4 & 1) * 32 + (c4 & 2) * 4 + (isc ? 0 : 4);
        sts1(a, __byte_perm(v.x, v.y, 0x7632));
        sts1(a + 16, __byte_perm(v.z, v.w, 0x7632));
    } else if (i < 252) {
        sts4(sb + M_G + (i - 224) * 16, make_uint4(v.x & 0xFFFF0000u, v.y & 0xFFFF0000u, v.z & 0xFFFF0000u, v.w & 0xFFFF0000u));
    }
}
__device__ __forceinline__ int pass_f(int fs, int ps) { return 224 * fs + ((fs & 1) ? (ps == 0 ? 96 : ps == 1 ? 32 : 0) : (ps == 0 ? 0 : ps == 1 ? 128 : 192)); }
__device__ __forceinline__ constexpr uint32_t slot_off(int l) { return l * 16384; }
__device__ __forceinline__ constexpr int g1_slot(int s) { return s % 7; }
__device__ __noinline__ void x1_fix(const uint32_t* g, uint32_t sa, int s) {
#pragma unroll 1
    for (int k = 4 * s; k < 4 * s + 4;) {
        const uint4 v = ld_relaxed4((const uint4*)(g + k * 256));
        sts4(sa + k * 1024, v);
        k += 2 * __all_sync(~0u, min(min(v.x, v.y), min(v.z, v.w)) != 0u);
    }
    __syncwarp();
}
__device__ __forceinline__ void ln_coeffs(float mean, float msq, uint32_t& r2, uint32_t& n2) {
    const float rs = bf_round(rsqrtf(fmaxf(msq - mean * mean, 0.f) + 1e-5f));
    r2 = pack2(rs, rs);
    n2 = pack2(-mean * rs, -mean * rs);
}

#define LOADW bulk_e(dst, g_wd + (size_t)((f >> 5) * 4 + nq) * 1792, 7168, bar);
template <int sec> __device__ __forceinline__ void ring_loader(const Params& p, uint32_t sb_, int r_, int j_, int lane) {
    const uint32_t sb = opaque(sb_);
    const int r = opaque(r_), j = opaque(j_), nq = j >> 1, fs = 4 * (j & 1) + nq;
    const int fa = pass_f(fs, 0), fb = pass_f(fs, 1), fc = pass_f(fs, 2);
    const uint32_t* h2src = (const uint32_t*)__shfl_sync(~0u, (unsigned long long)(p.actb + (size_t)r * RB_WORDS + RB_H2), 0);
    const CUtensorMap* gmap = (const CUtensorMap*)__shfl_sync(~0u, (unsigned long long)(&p.ga + sec), 0);
#define BAR(i) (sb + M_BAR + 8 * (i))
#define kh (j & 1)
            int sl = 0;
#pragma unroll 1
            for (int s = 0; s < 28; s++) {
                if (s == 7) { wait_flags(g_flag + (8 * r + j) * 128 + 96 + lane, lds1(sb + M_EPOCH) + 1, 0xFFFFu); fence_async_global(); }
                const int ps = s < 14 ? 0 : s < 21 ? 1 : 2;
                const uint32_t half = ps < 2 ? 8192 : 4096;
                const int sp = sl;
                if (s >= PACE && s < PACE_END) mbar_wait(BAR(B_FULL + s - PACE), 0);
                mbar_wait(BAR(B_EMPTY + sp), (s >= 7 && s < 14) || s >= 21);
                expect_e(BAR(B_FULL + sp), half);
                tma3_e(sb + slot_off(sp) + sec * half, gmap + 2 * ps, 0, ps ? 64 * sl : 32 * s, ps == 0 ? fa >> 6 : ps == 1 ? fb >> 6 : fc >> 5, BAR(B_FULL + sp));
                sl = sl == 6 ? 0 : sl + 1;
            }
            if (!sec) PROFH(3);
#pragma unroll 1
            for (int e = 0; e < 4; e++) {
                const uint32_t dst = sb + slot_off(e) + sec * 8192, bar = BAR(B_FULL + e);
                const int f = (e < 2 ? fa + 64 * e : e == 2 ? fb : fc) + 32 * sec;
                mbar_wait(BAR(B_EMPTY + e), 0);
                expect_e(bar, e == 3 && sec ? 0 : 7168);
                if (!(e == 3 && sec)) { LOADW }
            }
            sl = 4;
            int e = 4;
#pragma unroll 1
            for (int grp = 0; grp < 9; grp++) {
                const int ps = grp >= 6 ? 2 : grp >= 3 ? 1 : 0;
                int sidx = grp - 3 * ps;
                if (sec && sidx == 0) { mbar_wait(BAR(B_HRDY + ps), 0); fence_async_global(); }
                sidx += sidx >= nq;
                int f = pass_f(4 * kh + sidx, ps);
#pragma unroll 1
                for (int k = 4 >> ps; k > 0; k--, e++, f += 32) {
                    const uint32_t dst = sb + slot_off(sl), bar = BAR(B_FULL + sl);
                    mbar_wait(BAR(B_EMPTY + sl), e >= 12 && e < 24);
                    if (e < WIN_END && e >= WIN) mbar_wait(BAR(B_FULL + (sl >= WIN ? sl - WIN : sl + 12 - WIN)), e - WIN >= 12);
                    expect_e(bar, sec ? 8192 : 7168);
                    if (!sec) { LOADW }
                    else bulk_e(dst + 8192, h2src + f * 64, 8192, bar);
                    sl = sl == 11 ? 0 : sl + 1;
                }
            }
            if (!sec) PROFH(4);
}

#define PROF_PARAMS
#define PROF_ARGS
__device__ __noinline__ void helper_late(const Params& p, int r_, int j_, int warp_ PROF_PARAMS) {
    extern __shared__ __align__(1024) unsigned char smem[];
    const uint32_t sb = (uint32_t)__cvta_generic_to_shared(smem);
    const int r = opaque(r_), j = opaque(j_), warp = opaque(warp_), nq = j >> 1, b = 8 * r + j;
    uint32_t* const act = (uint32_t*)__shfl_sync(~0u, (unsigned long long)(p.actb + (size_t)r * RB_WORDS), 0);
    {
        const int lane = fresh_tid() & 31;
        const uint32_t target = lds1(sb + M_EPOCH) + 1;
        if (warp == 8) { expect_e(BAR(B_XCH), 14336); expect_e(BAR(B_XCH + 1), 14336); }
            if (warp == 9) {
#pragma unroll 1
                for (int kv = 0; kv < 2; kv++) {
                    mbar_wait(BAR(B_PUB + kv), 0);
                    wait_flags(g_flag + b * 128 + lane, target, (r >= 2 ? 6u : r == 1 ? 2u : 0u) << (8 * kv));
                    fence_async_global();
                    const uint32_t dst = sb + OFF_Y + (kv ? Y_VR : Y_K);
                    expect_e(BAR(B_KRFULL + kv), r >= 2 ? 28672 : r == 1 ? 14336 : 0);
                    if (r >= 2) bulk_e(dst, act - 2 * RB_WORDS + RB_KV + j * 7168 + kv * 3584, 14336, BAR(B_KRFULL + kv));
                    if (r >= 1) bulk_e(dst + 14336, act - RB_WORDS + RB_KV + j * 7168 + kv * 3584, 14336, BAR(B_KRFULL + kv));
                }
            } else if (warp == 8) {
                uint4 v[8];
                mbar_wait(BAR(B_WOFULL), 0);
#pragma unroll
                for (int k = 0; k < 8; k++) v[k] = ld_relaxed4(mod_src(lane + 32 * k, r, j, true));
#pragma unroll
                for (int k = 0; k < 8; k++) mod_store(sb, v[k], mod_src(lane + 32 * k, r, j, true), lane + 32 * k);
                warp_arrive(BAR(B_MOD1));
            } else if (warp == 11) {
                if (kh == 1 && r < 14) {
                    const uint32_t wmbuf = sb + OFF_X + HALF;
                    const int mcol = 2 * DM + 32 * (4 * r + nq);
                    mbar_wait(BAR(B_XFREE), 0);
                    tma3_e(wmbuf, &p.wm2, mcol, 0, 0, BAR(B_WMFULL));
                    tma3_e(wmbuf + 14336, &p.wm2, mcol, 224, 0, BAR(B_WMFULL));
#pragma unroll 1
                    for (int wd = lane; wd < 224; wd += 32) {
                        const uint32_t cb = __ldg((const uint32_t*)p.c + wd);
                        sts1(wmbuf + 28672 + (wd >> 3) * 32 + (wd & 3) * 8 + (wd & 4), pack2(silu_bf(cb & 0xFFFFu), silu_bf(cb >> 16)));
                    }
                    __syncwarp();
                    mbar_wait(BAR(B_WMFULL), 0);
                    const uint32_t wa = wmbuf + (8 * (lane >> 4) + (lane & 7)) * 64 + ((lane >> 3) & 1) * 16;
                    float d[2][4] = {};
#pragma unroll 4
                    for (int ks = 0; ks < 28; ks++) {
                        uint32_t A[8];
                        ldsm4t(wa + ks * 1024, A); ldsm4t(wa + ks * 1024 + 32, A + 4);
                        const float2 v = lds2f(wmbuf + 28672 + ks * 32 + (lane & 3) * 8);
                        mma16816(d[0], A[0], A[1], A[2], A[3], __float_as_uint(v.x), __float_as_uint(v.y));
                        mma16816(d[1], A[4], A[5], A[6], A[7], __float_as_uint(v.x), __float_as_uint(v.y));
                    }
                    const int q = lane & 3, col = mcol + 8 * q + (lane >> 2);
                    const uint32_t word = mod_word(q == 0 ? d[0][0] : q == 1 ? d[0][2] : q == 2 ? d[1][0] : d[1][2], col, target);
#pragma unroll
                    for (int i = 0; i < 8; i++) st_relaxed(g_mod + i * 6 * DM + col, word);
                }
                warp_arrive(BAR(B_WMFREE));
                mbar_wait(BAR(B_VRFULL), 0);
                l2_prefetch_e((const char*)p.wg + (size_t)b * 12544, 12544);
                l2_prefetch_e((const char*)p.wu + (size_t)b * 12544, 12544);
#pragma unroll 1
                for (int k = 0; k < (r < 12 ? 2 : 1); k++) {
                    const int u = 28 * kh + r + 16 * k;
                    expect_e(BAR(B_XFULL + k), 7168);
                    tma3_e(sb + OFF_Y + 102400, &p.dn, 0, 32 * u, 7 * j, BAR(B_XFULL + k));
                    tma3_e(sb + OFF_Y + 102400 + 3584, &p.dn, 0, 32 * u, 7 * (j ^ 1), BAR(B_XFULL + k));
                    mbar_wait(BAR(B_XFULL + k), 1);
                    asm volatile("{\n.reg .pred p;\nelect.sync _|p, 0xffffffff;\n@p cp.async.bulk.global.shared::cta.bulk_group [%0], [%1], 7168;\n"
                                 "cp.async.bulk.commit_group;\ncp.async.bulk.wait_group 0;\n}" ::"l"(g_wd + (size_t)(u * 4 + nq) * 1792), "r"(sb + OFF_Y + 102400) : "memory");
                    __syncwarp();
                }
                warp_arrive(BAR(B_FULLK));
                fence_gpu();
                if (lane < 16) st_relaxed(g_flag + (8 * lane + j) * 128 + 96 + r, target);
            }
        if (warp == 8 || warp == 11) {
            const int sec = warp == 11;
            if (sec) ring_loader<1>(p, sb, r, j, lane); else ring_loader<0>(p, sb, r, j, lane);
            mbar_wait(BAR(B_DONE), 0);
        } else if (warp == 9) {
#pragma unroll
            for (int ev = 0; ev < 4; ev++) { expect_e(BAR(B_GFULL + ev), ev < 2 ? HALF / 2 : 16384 + 4096); expect_e(BAR(B_XFULL + 2 + ev), ev < 2 ? HALF / 2 : HALF - 16384); }
            mbar_wait(BAR(B_PUB + 2), 0);
            const uint32_t* fp = g_flag + b * 128 + 32 + lane;
            const int par = (target - 1) & 1;
#pragma unroll 1
            for (int n = 0, ev = 0; ev < 4; n++) {
                if (ev == 1) mbar_wait(BAR(B_PUB + 3), 0);
                uint32_t ok = __ballot_sync(~0u, (int)(ld_relaxed(fp) - target) >= 0) >> (8 * ev);
                while ((ok & 0xFFu) == 0xFFu) {
                    if (ev == 1) mbar_wait(BAR(B_FULLK), 1);
                    asm volatile("fence.acquire.gpu;" ::: "memory");
                    fence_async_global();
                    const int tile = (ev & 1) + (ev >> 1) * par * 2;
                    const uint32_t dst = sb + (ev == 0 ? OFF_X : OFF_Y + (ev & 1) * HALF), first = ev < 2 ? HALF / 2 : 16384;
                    const char* src = (const char*)(act + RB_O + ((ev >> 1) * 2 + tile) * 14336);
                    if (ev >= 2) bulk_e(sb + OFF_X + X_STAT + (ev & 1) * 49152, act + RB_ST + tile * 1024, 4096, BAR(B_GFULL + ev));
                    bulk_e(dst, src, first, BAR(B_GFULL + ev));
                    bulk_e(dst + first, src + first, HALF - first, BAR(B_XFULL + 2 + ev));
                    if (ev) PROFH(4 + ev);
                    ev++; ok >>= 8;
                }
                if (n > SPIN_LIMIT) __trap();
            }
            mbar_wait(BAR(B_XFULL + 5), 1);
#pragma unroll 1
            for (int hf = 0; hf < 2; hf++) {
                const int tile = (par ^ 1) * 2 + hf;
                uint4* xz = (uint4*)(act + RB_X1 + tile * 14336 + j * 1792) + lane;
#pragma unroll
                for (int i = 0; i < 14; i++) xz[i * 32] = make_uint4(0, 0, 0, 0);
                ((uint4*)(act + RB_ST + (tile * 8 + j) * 128))[lane] = make_uint4(0, 0, 0, 0);
            }
#pragma unroll 1
            for (int ps = 0; ps < 3; ps++) {
                mbar_wait(BAR(B_PUB + 6 + ps), 0);
                wait_flags(g_flag + b * 128 + 64 + lane, target, (0x55u << kh) << (8 * ps));
                warp_arrive(BAR(B_HRDY + ps));
                PROFH(9 + ps);
            }
        } else {
#pragma unroll 1
            for (int k = 0; k < 9; k++) {
                uint32_t* fp = k < 2 ? g_flag + (b + 8 * lane) * 128 + k * 8 + lane : g_flag + (8 * r + lane) * 128 + 16 + k * 8 + j;
                mbar_wait(BAR(B_PUB + k), 0);
                if (k != 4 && k != 5) fence_gpu();
                if (k < 2 ? (lane == 1 || lane == 2) : lane < 8) st_relaxed(fp, target);
                if (k >= 3 && k <= 5) PROFH(k - 3);
            }
        }
    }
}

__global__ void __cluster_dims__(2, 1, 1) __launch_bounds__(384, 1) fused_block_kernel(const __grid_constant__ Params p) {
    extern __shared__ __align__(1024) unsigned char smem[];
    const uint32_t sb = (uint32_t)__cvta_generic_to_shared(smem);
    const int tid = threadIdx.x, lane = tid & 31, warp = __shfl_sync(~0u, tid >> 5, 0);
    const int m = blockIdx.x >> 1;
    int r, nq;
    if (m < 4) { r = 15; nq = m; }
    else if (m < 36) { r = (m - 4) & 7; nq = (m - 4) >> 3; }
    else { nq = (m - 36) / 7; r = m - 28 - 7 * nq; }
    const int j = opaque(2 * nq + (blockIdx.x & 1)), b = 8 * r + j, fs = 4 * kh + nq;
#define act (p.actb + (size_t)r * RB_WORDS)
    constexpr uint32_t sc = 0;
    if (lane == 0 && warp < 9 && warp != 6 && warp != 7) {
        const int i0 = warp == 8 ? 0 : 8 + 8 * warp, cnt = warp == 0 || warp == 8 ? 1 : warp < 3 ? 2 : 8;
#pragma unroll
        for (int k = 0; k < 8; k++) if (i0 + k != B_WMFULL) mbar_init(BAR(i0 + k), cnt);
        asm volatile("fence.mbarrier_init.release.cluster;" ::: "memory");
        fence_async_smem();
    }

    if (warp >= 8) {
        const int lane = fresh_tid() & 31;
        const bool early = kh == 0, gemv = r < 14;
        const int mcol = early ? 16 * (4 * r + nq) : 2 * DM + 32 * (4 * r + nq);
        const uint32_t wmbuf = sb + OFF_Y + HALF;
        asm volatile("setmaxnreg.dec.sync.aligned.u32 56;");
        if (warp == 9) {
#pragma unroll
            for (int i = 56; i < 64; i++) init_e(BAR(i), 1);
            fence_async_smem();
        }
        if (warp == 8) { init_e(BAR(B_WMFULL), 1); fence_async_smem(); }
        bar_arrive(0, 384);
        asm volatile("barrier.cluster.arrive.relaxed.aligned;" ::: "memory");
        if (warp == 8) {
            if (!sc) {
                expect_e(BAR(B_WMFULL), gemv ? 28672 >> early : 0);
                if (early && gemv) { tma3_e(wmbuf, &p.wm, mcol, 0, 0, BAR(B_WMFULL)); tma3_e(wmbuf + 7168, &p.wm, mcol, 224, 0, BAR(B_WMFULL)); }
#pragma unroll 1
                for (int kb = 0; kb < 7; kb++) {
                    expect_e(BAR(B_XFULL + kb), 16384);
                    tma3_e(sb + OFF_X + kb * 16384, &p.xm, 64 * kb, 128 * r, 0, BAR(B_XFULL + kb));
                }
            }
#pragma unroll 1
            for (int mt = 0; mt < 4; mt++) {
                if (mt == 1) bar_sync(9, 384);
                if (mt == 3) mbar_wait(BAR(B_WMFREE), 0);
                if (mt) mbar_wait(BAR(mt == 1 ? B_MOD1 : mt == 2 ? B_XFREE : B_VRFULL), 0);
                const uint32_t bar = BAR(mt == 3 ? B_WOFULL : B_FULLK + mt), dst = sb + (mt < 2 ? OFF_Y : OFF_X) + (mt & 1) * HALF;
                const int c0 = (mt < 2 ? DM + DM * mt : 0) + 56 * j - 8 * kh;
                if (!sc) {
                    expect_e(bar, HALF);
                    tma3_e(dst, mt == 3 ? &p.wo : &p.qkv, c0, 0, 0, bar);
                    tma3_e(dst + HALF / 2, mt == 3 ? &p.wo : &p.qkv, c0, 224, 0, bar);
                }
            }
        } else {
            if (warp == 10 && !sc) l2_prefetch_e((const char*)p.wqkv + (size_t)b * 9408, 9408);
            bar_sync(9, 384);
            if (sc) return;
            if (warp == 11 && early) {
                const uint32_t target = lds1(sb + M_EPOCH) + 1;
                mbar_wait(BAR(B_GEMV), 0);
                float sum = 0.f;
#pragma unroll
                for (int i = 0; i < 8; i++) sum += *(const float*)(smem + OFF_Y + HALF + 29696 + (i * 16 + (lane & 15)) * 4);
                uint32_t* mg = g_mod + mcol + (lane & 15) + (lane >> 4) * 4 * 6 * DM;
                const uint32_t word = mod_word(sum, mcol, target);
                if (gemv) { st_relaxed(mg, word); st_relaxed(mg + 6 * DM, word); st_relaxed(mg + 12 * DM, word); st_relaxed(mg + 18 * DM, word); }
            }
        }
    }
    if (LIKELY(warp < 8)) {
        const int w = warp >> 2, wi = warp & 3;
#define COORDS const int t = fresh_tid() & 127, lane = t & 31, q = lane & 3, lr = lane >> 2, ra = 64 * w + 16 * wi + lr; \
        const uint32_t lx = (lane >> 4) ^ (lane & 7), mrow = (64 * w + 16 * wi + ((lane >> 3) & 1) * 8 + (lane & 7)) * 128; \
        (void)q; (void)lr; (void)ra; (void)lx; (void)mrow;
        const int sid = 2 * (j & 3) + w;
#define RUN(k) (!sc || sid == (k))
#define WAIT(i, par) mbar_wait_c(BAR(i), (par) | sc)
        constexpr uint64_t DB128 = dconst(4096, 1024, 1);
        {
            const int wd = fresh_tid();
            const uint32_t cb = wd < 224 ? __ldg((const uint32_t*)p.c + wd) : 0u;
            if (wd == 255 && !sc) sts1(sb + M_EPOCH, atomicAdd(&g_ticket, 1u) / NCTA);
            sts1(sb + OFF_Y + HALF + 28672 + (wd >> 3) * 32 + (wd & 3) * 8 + (wd & 4), pack2(silu_bf(cb & 0xFFFFu), silu_bf(cb >> 16)));
        }
        bar_arrive(9, 384);
        bar_sync(0, 384);
        asm volatile("barrier.cluster.arrive.relaxed.aligned;" ::: "memory");
        asm volatile("setmaxnreg.inc.sync.aligned.u32 224;");
        PROFC(0);
        uint32_t xr[16];
        {
            COORDS
            uint32_t h[112];
            uint32_t ra2, na2, rb2, nb2;
            const int mi = min(128 * w + t, 223);
            const uint4* msrc = mod_src(mi, r, j, false);
            uint4 mv;
            {
                float ds[4] = {}, da[2][4] = {}, db[2][4] = {};
                const uint32_t ONE2 = 0x3F803F80u;
#pragma unroll
                for (int kb = 0; kb < 7; kb++) {
                    if (kb == GEMV_AT && kh == 0) { WAIT(B_WMFULL, 0); gemv_part(sb + OFF_Y + HALF, warp, lane); warp_arrive(BAR(B_GEMV)); }
                    WAIT(B_XFULL + kb, 0);
#pragma unroll
                    for (int k4 = 0; k4 < 4; k4++) ldsm4(sb + OFF_X + mrow + kb * 16384 + (((2 * k4) ^ lx) << 4), h + 16 * kb + 4 * k4);
#pragma unroll
                    for (int k4 = 0; k4 < 4; k4++) {
                        const uint32_t* f = h + 16 * kb + 4 * k4;
                        mma16816(ds, f[0], f[1], f[2], f[3], ONE2, ONE2);
                        mma1688(da[0], f[0], f[1], f[0]); mma1688(db[0], f[0], f[1], f[1]);
                        mma1688(da[1], f[2], f[3], f[2]); mma1688(db[1], f[2], f[3], f[3]);
                    }
                }
#pragma unroll
                for (int i = 0; i < 4; i++) {
                    const int ch = 7 * j + 2 * i + (lane >> 4);
                    ldsm4(sb + OFF_X + mrow + (ch >> 3) * 16384 + (((ch ^ lane) & 7) << 4), xr + 4 * i);
                }
                mv = ld_relaxed4(msrc);
                warp_arrive(BAR(B_XFREE));
                float qa = (lr & 1) ? da[0][1] + da[1][1] : da[0][0] + da[1][0];
                float qb = (lr & 1) ? db[0][3] + db[1][3] : db[0][2] + db[1][2];
                const int src = (lane & ~3) | (lr >> 1);
                qa = __shfl_sync(~0u, qa, src);
                qb = __shfl_sync(~0u, qb, src);
                ln_coeffs(ds[0] * (1.f / DM), qa * (1.f / DM), ra2, na2);
                ln_coeffs(ds[2] * (1.f / DM), qb * (1.f / DM), rb2, nb2);
#pragma unroll
                for (int i = 0; i < 4 * NPRE; i += 2) { h[i] = hfma2(h[i], ra2, na2); h[i + 1] = hfma2(h[i + 1], rb2, nb2); }
            }
            PROFC(1);
            {
                float ak[28], av[28], aq[28];
                uint32_t kp[14], vp[14];
                const uint64_t bq0 = (DB128 & ~0xFFFFFFFFull) | (mkdesc(sb + OFF_X, DB128) + kh), bk0 = bq0 + (OFF_Y >> 4), bv0 = bk0 + (HALF >> 4);
                uint32_t* kvg = act + RB_KV + j * 7168 + (8 * w + 2 * wi) * 224 + lane;
                mod_store(sb, mv, msrc, mi);
                bar_sync(3, 256);
                if (warp == 0) warp_arrive(BAR(B_MOD1));
                WAIT(B_FULLK, 0);
                PROFC(2);
                reg_def<28>(ak);
#pragma unroll
                for (int g4 = 0; g4 < 4; g4++) {
#pragma unroll
                    for (int ks = 7 * g4; ks < 7 * g4 + 7; ks++) {
                        const uint4 st = *(const uint4*)(smem + M_ST + ks * 64 + q * 16);
                        if (ks >= NPRE) {
                            h[4 * ks] = hfma2(h[4 * ks], ra2, na2); h[4 * ks + 1] = hfma2(h[4 * ks + 1], rb2, nb2);
                            h[4 * ks + 2] = hfma2(h[4 * ks + 2], ra2, na2); h[4 * ks + 3] = hfma2(h[4 * ks + 3], rb2, nb2);
                        }
                        h[4 * ks] = hfma2(h[4 * ks], st.x, st.y); h[4 * ks + 1] = hfma2(h[4 * ks + 1], st.x, st.y);
                        h[4 * ks + 2] = hfma2(h[4 * ks + 2], st.z, st.w); h[4 * ks + 3] = hfma2(h[4 * ks + 3], st.z, st.w);
                    }
                    WG_FENCE();
#pragma unroll
                    for (int ks = 7 * g4; ks < 7 * g4 + 7; ks++) wgmma_rl_56(ak, h[4 * ks], h[4 * ks + 1], h[4 * ks + 2], h[4 * ks + 3], bk0 + ks * 128, ks != 0);
                }
                WG_COMMIT();
                PROFC(3);
                WAIT(B_FULLV, 0);
                reg_def<28>(av);
                WG_FENCE();
#pragma unroll
                for (int ks = 0; ks < 8; ks++) wgmma_rl_56(av, h[4 * ks], h[4 * ks + 1], h[4 * ks + 2], h[4 * ks + 3], bv0 + ks * 128, ks != 0);
                WG_COMMIT();
                WG_WAIT(1);
                reg_fence<28>(ak);
#pragma unroll
                for (int g = 0; g < 7; g++) {
                    kp[2 * g] = pack2(ak[4 * g], ak[4 * g + 1]); kp[2 * g + 1] = pack2(ak[4 * g + 2], ak[4 * g + 3]);
                    kvg[g * 32] = kp[2 * g]; kvg[224 + g * 32] = kp[2 * g + 1];
                }
                warp_arrive(BAR(B_PUB));
                PROFC(4);
                WG_FENCE();
#pragma unroll
                for (int ks = 8; ks < 28; ks++) wgmma_rl_56(av, h[4 * ks], h[4 * ks + 1], h[4 * ks + 2], h[4 * ks + 3], bv0 + ks * 128, 1);
                WG_COMMIT();
                WAIT(B_FULLQ, 0);
                reg_def<28>(aq);
                WG_FENCE();
#pragma unroll
                for (int ks = 0; ks < 8; ks++) wgmma_rl_56(aq, h[4 * ks], h[4 * ks + 1], h[4 * ks + 2], h[4 * ks + 3], bq0 + ks * 128, ks != 0);
                WG_COMMIT();
                WG_WAIT(1);
                reg_fence<28>(av);
#pragma unroll
                for (int g = 0; g < 7; g++) {
                    vp[2 * g] = pack2(av[4 * g], av[4 * g + 1]); vp[2 * g + 1] = pack2(av[4 * g + 2], av[4 * g + 3]);
                    kvg[3584 + g * 32] = vp[2 * g]; kvg[3584 + 224 + g * 32] = vp[2 * g + 1];
                }
                warp_arrive(BAR(B_PUB + 1));
                PROFC(5);
                WG_FENCE();
#pragma unroll
                for (int ks = 8; ks < 28; ks++) wgmma_rl_56(aq, h[4 * ks], h[4 * ks + 1], h[4 * ks + 2], h[4 * ks + 3], bq0 + ks * 128, 1);
                WG_COMMIT();
                WAIT(B_PUB + 1, 0);
                const uint32_t rg = 8 * w + 2 * wi + ((lane >> 3) & 1);
                const uint32_t ko = sb + OFF_Y + Y_KOWN + rg * 896 + (lane & 7) * 16, qo = sb + OFF_Y + Y_Q + rg * 1024 + (lane >> 4) * 128 + (lane & 7) * 16;
#pragma unroll
                for (int g = 0; g < 6; g += 2) {
                    stsm4(ko + (g + (lane >> 4)) * 128, kp[2 * g], kp[2 * g + 1], kp[2 * g + 2], kp[2 * g + 3]);
                    stsm4(ko + (Y_VOWN - Y_KOWN) + (g + (lane >> 4)) * 128, vp[2 * g], vp[2 * g + 1], vp[2 * g + 2], vp[2 * g + 3]);
                }
                stsm4(ko + (lane >> 4) * (Y_VOWN - Y_KOWN) + 6 * 128, kp[12], kp[13], vp[12], vp[13]);
                WG_WAIT(0);
                reg_fence<28>(aq);
                __syncwarp();
                if (lane < 3 && w == 1) mbar_arrive(BAR(B_EMPTY + lane));
                uint32_t qp[14];
#pragma unroll
                for (int i = 0; i < 14; i++) qp[i] = pack2(aq[2 * i], aq[2 * i + 1]);
                stsm4(qo, qp[0], qp[1], qp[2], qp[3]);
                stsm4(qo + 256, qp[4], qp[5], q < 2 ? qp[6] : 0u, q < 2 ? qp[7] : 0u);
                stsm4(qo + 512, q < 2 ? 0u : qp[6], q < 2 ? 0u : qp[7], qp[8], qp[9]);
                stsm4(qo + 768, qp[10], qp[11], qp[12], qp[13]);
                if (!sc) bar_sync(3, 256);
            }
        }
        PROFC(6);
        WAIT(B_KRFULL, 0);
        PROFC(7);
        if (RUN(2)) {
#pragma unroll 1
            for (int hf = sc; hf < 2; hf++) {
                COORDS
                float s[136];
                float na = 0.f, nb = 0.f;
                const float CS = 0.18898223650461361f * 1.4426950408889634f;
                const int kg0 = 8 * hf + 2 * wi;
                const int pmin = 16 - 8 * r - 4 * hf - wi;
                const float NEG = __int_as_float(0xFF800000);
                {
                    uint32_t F[8];
                    const uint32_t qa = sb + OFF_Y + Y_Q + (kg0 + ((lane >> 3) & 1)) * 1024 + (4 * w + (lane >> 4)) * 128 + (lane & 7) * 16;
                    ldsm4(qa, F); ldsm4(qa + 256, F + 4);
                    uint32_t ka = sb + OFF_Y + Y_K + kg0 * 896 + (3 * w + (lane >> 3)) * 128 + (lane & 7) * 16;
#pragma unroll
                    for (int g = 0; g < 34; g++) {
                        uint32_t B[4];
                        if (g >= 12 && g % 4 == 0) ka += __float_as_uint(s[4 * (g - 12)]) & p.zero;
                        ldsm4(ka + g * 896, B);
                        mma16816_first(s + 4 * g, F[0], F[1], F[2], F[3], B[0], B[1]);
                        mma16816_v(s + 4 * g, F[4], F[5], F[6], F[7], B[2], B[3]);
                    }
                    const bool c0 = 2 * q > lr, c1 = 2 * q + 1 > lr;
                    if (!c0) { s[0] = NEG; s[6] = NEG; }
                    if (!c1) { s[1] = NEG; s[7] = NEG; }
                    s[2] = NEG; s[3] = NEG;
                    if (c0) { s[128] = NEG; s[134] = NEG; }
                    if (c1) { s[129] = NEG; s[135] = NEG; }
                    s[132] = NEG; s[133] = NEG;
                    float ma = NEG, mb = NEG;
#pragma unroll
                    for (int pp = 0; pp < 17; pp++) {
                        const float* e = s + 8 * pp;
                        const float bias = pp < pmin ? NEG : 0.f;
                        ma = fmaxf(ma, fmaxf(fmaxf(e[0], e[1]), fmaxf(e[4], e[5])) + bias);
                        mb = fmaxf(mb, fmaxf(fmaxf(e[2], e[3]), fmaxf(e[6], e[7])) + bias);
                    }
                    ma = fmaxf(ma, __shfl_xor_sync(~0u, ma, 1)); mb = fmaxf(mb, __shfl_xor_sync(~0u, mb, 1));
                    ma = fmaxf(ma, __shfl_xor_sync(~0u, ma, 2)); mb = fmaxf(mb, __shfl_xor_sync(~0u, mb, 2));
                    na = -ma * CS; nb = -mb * CS;
                }
                PROFC(8 + 3 * hf);
                {
                    WAIT(B_VRFULL, 0);
                    float o[16] = {}, rs[4] = {};
                    uint32_t pk[2];
                    const uint32_t va = sb + OFF_Y + Y_VR + (kg0 + ((lane >> 3) & 1)) * 896 + (3 * w + (lane >> 4)) * 128 + (lane & 7) * 16;
#pragma unroll
                    for (int pp = 0; pp < 17; pp++) {
                        uint32_t B[8];
                        const uint32_t v = va + pp * 1792 + (pp == 16 || (pp >= 9 && kg0 + 2 * pp >= 32) ? Y_VOWN - 32 * 896 : 0);
                        ldsm4t(v, B); ldsm4t(v + 256, B + 4);
                        float e[8];
                        const float bias = __uint_as_float((pp < pmin ? 0xFF800000u : 0u) | ((pp < 2 ? B[0] : pk[pp & 1]) & p.zero));
#pragma unroll
                        for (int i = 0; i < 8; i++) e[i] = ex2(fmaf(s[8 * pp + i], CS, ((i & 2) ? nb : na) + bias));
                        const uint32_t p0 = pack2(e[0], e[1]), p1 = pack2(e[2], e[3]), p2 = pack2(e[4], e[5]), p3 = pack2(e[6], e[7]);
                        pk[pp & 1] = p3;
                        mma16816(rs, p0, p1, p2, p3, 0x3F803F80u, 0x3F803F80u);
#pragma unroll
                        for (int g = 0; g < 4; g++) mma16816(o + 4 * g, p0, p1, p2, p3, B[2 * g], B[2 * g + 1]);
                    }
                    PROFC(9 + 3 * hf);
                    const float ia = rcp(rs[0]), ib = rcp(rs[2]);
                    uint32_t* og = act + RB_O + hf * 14336 + (7 * j + 3 * w) * 256 + wi * 64 + lane;
#pragma unroll
                    for (int g = 0; g < 4; g++) {
                        if ((g == 3 - 3 * w) ? ((q >> 1) == w) : true) {
                            og[g * 256] = pack2(o[4 * g] * ia, o[4 * g + 1] * ia);
                            og[g * 256 + 32] = pack2(o[4 * g + 2] * ib, o[4 * g + 3] * ib);
                        }
                    }
                    warp_arrive(BAR(B_PUB + 2 + hf));
                    PROFC(10 + 3 * hf);
                }
            }
        }
        uint32_t x1p[14];
        COORDS
        constexpr uint64_t DT = dconst(1024, 128, 0);
        const int tile = opaque((lds1(sb + M_EPOCH) & 1) * 2 + w);
        if (RUN(4)) {
            float ac[28];
            const uint32_t ad = mkdesc(sb + (w ? OFF_Y + HALF : OFF_X), DT), bd = mkdesc(sb + OFF_X + HALF, DB128) + kh;
            WAIT(B_WOFULL, 0);
            WAIT(B_MOD1, 1);
            WAIT(B_GFULL + w, 0);
            PROFC(28);
            reg_def<28>(ac);
#pragma unroll 1
            for (int u = 0; u < 4; u++) {
                if (u == 2) WAIT(B_XFULL + 2 + w, 1);
                WG_FENCE();
#pragma unroll
                for (int i = 0; i < 7; i++) wgmma_ss_56<DT, DB128>(ac, ad + (7 * u + i) * 128, bd + (7 * u + i) * 128, (u | i) != 0);
            }
            WG_COMMIT();
            WG_WAIT(0);
            reg_fence<28>(ac);
            PROFC(14);
            __syncwarp();
            if (lane < 3) mbar_arrive(BAR(B_EMPTY + 4 - w + lane));
            if (lane < 3 && w == 0) mbar_arrive(BAR(B_EMPTY + lane));
            float ds[4] = {}, da[4] = {}, db[4] = {};
            uint32_t* xo = act + RB_X1 + tile * 14336 + 7 * j * 256 + wi * 64 + lane;
#pragma unroll
            for (int g = 0; g < 7; g++) {
                const float2 ga = *(const float2*)(smem + M_G + (8 * g + 2 * q) * 4);
                x1p[2 * g] = pack2(fmaf(ga.x, ac[4 * g], bf_lo(xr[2 * g])), fmaf(ga.y, ac[4 * g + 1], bf_hi(xr[2 * g])));
                x1p[2 * g + 1] = pack2(fmaf(ga.x, ac[4 * g + 2], bf_lo(xr[2 * g + 1])), fmaf(ga.y, ac[4 * g + 3], bf_hi(xr[2 * g + 1])));
                st_relaxed(xo + g * 256, nz(x1p[2 * g])); st_relaxed(xo + g * 256 + 32, nz(x1p[2 * g + 1]));
                mma1688(ds, x1p[2 * g], x1p[2 * g + 1], 0x3F803F80u);
                mma1688(da, x1p[2 * g], x1p[2 * g + 1], x1p[2 * g]);
                mma1688(db, x1p[2 * g], x1p[2 * g + 1], x1p[2 * g + 1]);
            }
            const int src = (lane & ~3) | (lr >> 1);
            const float qa = __shfl_sync(~0u, (lr & 1) ? da[1] : da[0], src), qb = __shfl_sync(~0u, (lr & 1) ? db[3] : db[2], src);
            const float kk = (q & 1) ? ((q & 2) ? qb : qa) : ((q & 2) ? ds[2] : ds[0]);
            st_relaxed(act + RB_ST + ((tile * 8 + j) * 64 + 16 * wi + lr + 4 * (q & 2)) * 2 + (q & 1), nz(__float_as_uint(kk)));
            __syncwarp();
            if (lane < 2) mbar_arrive(BAR(B_PUB + 4 + w));
        } else reg_def<14>(x1p);
        PROFC(15);
        uint32_t h2a[32], h2b[24];
        {
            const int fa = pass_f(fs, 0), fb = pass_f(fs, 1), fc = pass_f(fs, 2);
            uint32_t* h2g = act + RB_H2 + (8 * w + 2 * wi) * 32 + lane;
            const uint32_t a0 = mkdesc(sb + OFF_Y + w * HALF, DT);
            if (RUN(3)) {
                uint32_t ra2, na2, rb2, nb2;
                {
                    const uint32_t* sg = act + RB_ST + ((tile * 8 + 2 * q) * 64 + 16 * wi + lr) * 2;
                    uint2 u[4];
                    WAIT(B_GFULL + 2 + w, 0);
                    PROFC(16);
#pragma unroll
                    for (int i = 0; i < 4; i++) { const float2 v = lds2f(sb + OFF_X + X_STAT + w * 49152 + ((2 * q + (i >> 1)) * 64 + 16 * wi + lr + 8 * (i & 1)) * 8); u[i] = make_uint2(__float_as_uint(v.x), __float_as_uint(v.y)); }
                    while (__any_sync(~0u, min(min(min(u[0].x, u[0].y), min(u[1].x, u[1].y)), min(min(u[2].x, u[2].y), min(u[3].x, u[3].y))) < 1u - sc)) {
#pragma unroll
                        for (int i = 0; i < 4; i++) u[i] = ld_relaxed2(sg + (i >> 1) * 128 + (i & 1) * 16);
                    }
                    warp_arrive(BAR(B_EMPTY + 3 + 3 * w));
                    float v[4] = {__uint_as_float(u[0].x) + __uint_as_float(u[2].x), __uint_as_float(u[0].y) + __uint_as_float(u[2].y),
                                  __uint_as_float(u[1].x) + __uint_as_float(u[3].x), __uint_as_float(u[1].y) + __uint_as_float(u[3].y)};
#pragma unroll
                    for (int i = 0; i < 4; i++) { v[i] += __shfl_xor_sync(~0u, v[i], 1); v[i] += __shfl_xor_sync(~0u, v[i], 2); }
                    ln_coeffs(v[0] * (1.f / DM), v[1] * (1.f / DM), ra2, na2);
                    ln_coeffs(v[2] * (1.f / DM), v[3] * (1.f / DM), rb2, nb2);
                }
                const uint32_t ha = sb + OFF_Y + w * HALF + (lane >> 4) * 1024 + (2 * wi + ((lane >> 3) & 1)) * 128 + (lane & 7) * 16;
                const uint32_t sta = sb + M_ST + q * 16;
                const uint32_t* xg = act + RB_X1 + tile * 14336 + (lane >> 4) * 256 + wi * 64 + (lane & 15) * 4;
                uint32_t x[8];
                const uint32_t xs = sb + OFF_Y + w * HALF + (lane >> 4) * 1024 + wi * 256 + (lane & 15) * 16;
                uint4 st[2];
                auto load = [&](int s) {
                    if (s == 4) mbar_wait_c(BAR(B_XFULL + 4 + w), 1);
                    ldsm4(ha + s * 4096, x); ldsm4(ha + s * 4096 + 2048, x + 4);
                    st[0] = lds4(sta + s * 128); st[1] = lds4(sta + s * 128 + 64);
                };
                auto prep = [&](int s, uint32_t* f) {
                    if (__any_sync(~0u, min(min(min(x[0], x[1]), min(x[2], x[3])), min(min(x[4], x[5]), min(x[6], x[7]))) < 1u - sc)) {
                        WG_WAIT(0);
                        x1_fix(xg, xs, s);
                        ldsm4(ha + s * 4096, x); ldsm4(ha + s * 4096 + 2048, x + 4);
                    }
#pragma unroll
                    for (int i = 0; i < 2; i++) {
                        f[4 * i] = hfma2(hfma2(x[4 * i], ra2, na2), st[i].x, st[i].y); f[4 * i + 1] = hfma2(hfma2(x[4 * i + 1], rb2, nb2), st[i].x, st[i].y);
                        f[4 * i + 2] = hfma2(hfma2(x[4 * i + 2], ra2, na2), st[i].z, st[i].w); f[4 * i + 3] = hfma2(hfma2(x[4 * i + 3], rb2, nb2), st[i].z, st[i].w);
                    }
                    if (s < 13) load(s + 1);
                    stsm4(ha + s * 4096, f[0], f[1], f[2], f[3]); stsm4(ha + s * 4096 + 2048, f[4], f[5], f[6], f[7]);
                };
                float ac[128];
                uint32_t fr[3][8];
                uint64_t bd = (DB128 & ~0xFFFFFFFFull) | mkdesc(sb, DB128);
                reg_def<128>(ac);
                load(0);
                prep(0, fr[0]);
                PROFC(17);
#pragma unroll
                for (int s = 0; s < 14; s++) {
                    const uint32_t* f = fr[s % 3];
                    WAIT(B_FULL + g1_slot(s), s >= 7);
                    WG_FENCE();
                    wgmma_rl_256(ac, f[0], f[1], f[2], f[3], bd, s != 0);
                    wgmma_rl_256(ac, f[4], f[5], f[6], f[7], bd + 128, 1);
                    bd += s == 6 ? p.zero - 6 * 1024ull : 1024;
                    WG_COMMIT();
                    if (s < 13) prep(s + 1, fr[(s + 1) % 3]);
                    if (s > 0) { WG_WAIT(1); warp_arrive(BAR(B_EMPTY + g1_slot(s - 1))); }
                }
                fence_async_smem();
                PROFC(18);
                WG_WAIT(0);
                reg_fence<128>(ac);
                warp_arrive(BAR(B_EMPTY + 6));
#pragma unroll
                for (int g = 0; g < 16; g++) {
                    h2a[2 * g] = hmul2(pack2_relu(ac[4 * g], ac[4 * g + 1]), pack2(ac[64 + 4 * g], ac[64 + 4 * g + 1]));
                    h2a[2 * g + 1] = hmul2(pack2_relu(ac[4 * g + 2], ac[4 * g + 3]), pack2(ac[64 + 4 * g + 2], ac[64 + 4 * g + 3]));
                }
                bar_sync(1 + w, 128);
            } else reg_def<32>(h2a);
            PROFC(19);
            if (RUN(5)) {
                float ac[64];
                reg_def<64>(ac);
                const uint32_t bx = mkdesc(sb, dconst(8192, 1024, 1));
#pragma unroll kB
                for (int s = 0; s < 7; s++) {
                    WAIT(B_FULL + s, 0);
                    const uint32_t ad = a0 + s * 512, bd = bx + (slot_off(s) >> 4);
                    WG_FENCE();
#pragma unroll
                    for (int k = 0; k < 4; k++) wgmma_ss_128<DT, DB128>(ac, ad + k * 128, bd + k * 128, (s | k) != 0);
                    WG_COMMIT();
                    if (s == 1) {
#pragma unroll
                        for (int g = 0; g < 16; g++) { h2g[(fa / 8 + g) * 512] = h2a[2 * g]; h2g[(fa / 8 + g) * 512 + 32] = h2a[2 * g + 1]; }
                        warp_arrive(BAR(B_PUB + 6));
                    }
                    if (s > 0) { WG_WAIT(1); warp_arrive(BAR(B_EMPTY + s - 1)); }
                }
                WG_WAIT(0);
                reg_fence<64>(ac);
                warp_arrive(BAR(B_EMPTY + 6));
#pragma unroll
                for (int g = 0; g < 8; g++) {
                    h2b[2 * g] = hmul2(pack2_relu(ac[4 * g], ac[4 * g + 1]), pack2(ac[32 + 4 * g], ac[32 + 4 * g + 1]));
                    h2b[2 * g + 1] = hmul2(pack2_relu(ac[4 * g + 2], ac[4 * g + 3]), pack2(ac[32 + 4 * g + 2], ac[32 + 4 * g + 3]));
                }
            } else reg_def<16>(h2b);
            PROFC(27);
            if (RUN(6)) {
                float ac[32];
                reg_def<32>(ac);
                const uint32_t bx = mkdesc(sb, dconst(4096, 512, 2));
#pragma unroll kC
                for (int s = 0; s < 7; s++) {
                    WAIT(B_FULL + s, 1);
                    const uint32_t ad = a0 + s * 512, bd = bx + (slot_off(s) >> 4);
                    WG_FENCE();
#pragma unroll
                    for (int k = 0; k < 4; k++) wgmma_ss_64<DT, dconst(4096, 512, 2)>(ac, ad + k * 128, bd + k * 64, (s | k) != 0);
                    WG_COMMIT();
                    if (s == 1) {
#pragma unroll
                        for (int g = 0; g < 8; g++) { h2g[(fb / 8 + g) * 512] = h2b[2 * g]; h2g[(fb / 8 + g) * 512 + 32] = h2b[2 * g + 1]; }
                        warp_arrive(BAR(B_PUB + 7));
                    }
                    if (s > 0) { WG_WAIT(1); warp_arrive(BAR(B_EMPTY + s - 1)); }
                }
                WG_WAIT(0);
                reg_fence<32>(ac);
                __syncwarp();
                if (lane < 6) mbar_arrive(BAR(B_EMPTY + 6 + lane));
                PROFC(20);
#pragma unroll
                for (int g = 0; g < 4; g++) {
                    h2b[16 + 2 * g] = hmul2(pack2_relu(ac[4 * g], ac[4 * g + 1]), pack2(ac[16 + 4 * g], ac[16 + 4 * g + 1]));
                    h2b[16 + 2 * g + 1] = hmul2(pack2_relu(ac[4 * g + 2], ac[4 * g + 3]), pack2(ac[16 + 4 * g + 2], ac[16 + 4 * g + 3]));
                    h2g[(fc / 8 + g) * 512] = h2b[16 + 2 * g]; h2g[(fc / 8 + g) * 512 + 32] = h2b[16 + 2 * g + 1];
                }
                warp_arrive(BAR(B_PUB + 8));
                asm volatile("barrier.cluster.wait.aligned;" ::: "memory");
                if (lane == 0 && !sc) {
                    uint32_t rb;
                    asm volatile("mapa.shared::cluster.u32 %0, %1, %2;" : "=r"(rb) : "r"(BAR(B_PEER)), "r"(kh ^ 1));
                    asm volatile("mbarrier.arrive.relaxed.cluster.shared::cluster.b64 _, [%0];" ::"r"(rb) : "memory");
                }
            } else reg_def<8>(h2b + 16);
        }
        PROFC(21);
        if (RUN(7)) {
            float ac[56];
            reg_def<56>(ac);
            constexpr uint64_t DAN = dconst(2048, 128, 0);
            constexpr uint64_t DW = dconst(128, 512, 0);
            const uint32_t bx = mkdesc(sb, DW);
#pragma unroll
            for (int e = 0; e < 4; e++) {
                WAIT(B_FULL + e, 0);
                const uint64_t bd = ((DW & ~0xFFFFFFFFull) | bx) + (slot_off(e) >> 4);
                const uint32_t* hh = e < 2 ? h2a + 16 * e : h2b + 16 * (e - 2);
                WG_FENCE();
#pragma unroll
                for (int k = 0; k < (e < 3 ? 4 : 2); k++) wgmma_rl_112(ac, hh[4 * k], hh[4 * k + 1], hh[4 * k + 2], hh[4 * k + 3], bd + (k >> 1) * 512 + (k & 1) * 16, (e | k) != 0);
                WG_COMMIT();
                if (e > 0) { WG_WAIT(1); warp_arrive(BAR(B_EMPTY + e - 1)); }
            }
            PROFC(22);
            uint32_t ad = mkdesc(sb + 4 * 16384 + 8192 + w * 1024, DAN), bd = bx + 4 * 1024, fb_ = BAR(B_FULL + 4), eb_ = BAR(B_EMPTY + 3), par = sc;
#pragma unroll 1
            for (int e = 4; e < 25; e++) {
                mbar_wait_c(fb_, par);
                WG_FENCE();
                wgmma_ss_112<DAN, DW>(ac, ad, bd, 1);
                wgmma_ss_112<DAN, DW>(ac, ad + 256, bd + 16, 1);
                WG_COMMIT();
                WG_WAIT(1);
                warp_arrive(eb_);
                eb_ = fb_ + 8 * (B_EMPTY - B_FULL);
                ad += 1024; bd += 1024; fb_ += 8;
                if (e == 11 || e == 23) { ad -= 12 * 1024; bd -= 12 * 1024; fb_ -= 96; par = (par ^ 1) | sc; }
            }
            mbar_wait_cluster(BAR(B_PEER), sc);
            WG_WAIT(0);
            reg_fence<56>(ac);
            PROFC(24);
            uint32_t rdst, rbar;
            asm volatile("mapa.shared::cluster.u32 %0, %1, %2;" : "=r"(rdst) : "r"(sb + OFF_Y + (5 + w) * 16384 + t * 16), "r"(kh ^ 1 ^ sc));
            asm volatile("mapa.shared::cluster.u32 %0, %1, %2;" : "=r"(rbar) : "r"(BAR(B_XCH + w)), "r"(kh ^ 1 ^ sc));
#pragma unroll
            for (int g = 0; g < 7; g++) {
                const float v0 = ac[28 + 4 * g + 0], v1 = ac[28 + 4 * g + 1];
                const float v2 = ac[28 + 4 * g + 2], v3 = ac[28 + 4 * g + 3];
                if (!sc) asm volatile("st.async.shared::cluster.mbarrier::complete_tx::bytes.v4.f32 [%0], {%1,%2,%3,%4}, [%5];"
                             ::"r"(rdst + g * 2048), "f"(v0), "f"(v1), "f"(v2), "f"(v3), "r"(rbar) : "memory");
            }
            mbar_wait_cluster(BAR(B_XCH + w), sc);
            PROFC(25);
            uint32_t op[16];
#pragma unroll
            for (int g = 0; g < 7; g++) {
                const uint4 rv = *(const uint4*)(smem + OFF_Y + (5 + w) * 16384 + t * 16 + g * 2048);
                const float2 gb = *(const float2*)(smem + M_G + 224 + (8 * g + 2 * q) * 4);
                const float v0 = ac[4 * g + 0] + __uint_as_float(rv.x), v1 = ac[4 * g + 1] + __uint_as_float(rv.y);
                const float v2 = ac[4 * g + 2] + __uint_as_float(rv.z), v3 = ac[4 * g + 3] + __uint_as_float(rv.w);
                op[2 * g] = pack2(fmaf(gb.x, v0, bf_lo(x1p[2 * g])), fmaf(gb.y, v1, bf_hi(x1p[2 * g])));
                op[2 * g + 1] = pack2(fmaf(gb.x, v2, bf_lo(x1p[2 * g + 1])), fmaf(gb.y, v3, bf_hi(x1p[2 * g + 1])));
            }
            WAIT(B_EMPTY + 1, 0);
            const uint32_t oc = sb + OUT_STAGE + warp * 1792;
            const uint32_t oa = oc + (((lane >> 3) & 1) * 8 + (lane & 7)) * 112 + (lane >> 4) * 16;
            stsm4(oa, op[0], op[1], op[2], op[3]); stsm4(oa + 32, op[4], op[5], op[6], op[7]); stsm4(oa + 64, op[8], op[9], op[10], op[11]);
            asm volatile("stmatrix.sync.aligned.m8n8.x2.shared.b16 [%0], {%1,%2};" ::"r"(oa + 96), "r"(op[12]), "r"(op[13]));
            fence_async_smem();
            __syncwarp();
            asm volatile("{\n.reg .pred p;\nelect.sync _|p, 0xffffffff;\n@p cp.async.bulk.tensor.3d.global.shared::cta.bulk_group [%0, {%2, %3, %4}], [%1];\n"
                         "cp.async.bulk.commit_group;\ncp.async.bulk.wait_group.read 0;\n}" ::"l"(&p.om), "r"(oc), "r"(56 * j), "r"(128 * r + 16 * warp), "r"(0) : "memory");
        }
        PROFC(26);
        bar_sync(1 + w, 128);
        if (wi == 0) warp_arrive(BAR(B_DONE));
        return;
    }
    helper_late(p, r, j, warp PROF_ARGS);
}

#undef act
typedef CUresult (*EncodeFn)(CUtensorMap*, CUtensorMapDataType, cuuint32_t, void*, const cuuint64_t*, const cuuint64_t*, const cuuint32_t*,
                             const cuuint32_t*, CUtensorMapInterleave, CUtensorMapSwizzle, CUtensorMapL2promotion, CUtensorMapFloatOOBfill);

static void make_map(EncodeFn fn, CUtensorMap* m, const void* ptr, uint64_t d0, uint64_t d1, uint64_t d2, uint64_t s1, uint64_t s2,
                     uint32_t b0, uint32_t b1, uint32_t b2, CUtensorMapSwizzle sw) {
    cuuint64_t dims[3] = {d0, d1, d2}, strides[2] = {s1, s2};
    cuuint32_t box[3] = {b0, b1, b2}, es[3] = {1, 1, 1};
    CUresult rc = fn(m, CU_TENSOR_MAP_DATA_TYPE_BFLOAT16, 3, (void*)ptr, dims, strides, box, es, CU_TENSOR_MAP_INTERLEAVE_NONE, sw,
                     CU_TENSOR_MAP_L2_PROMOTION_L2_128B, CU_TENSOR_MAP_FLOAT_OOB_FILL_NONE);
    (void)rc;
}

extern "C" void kernel_launch(void* const* d_in, const int* in_sizes, int n_in, void* d_out, int out_size) {
    (void)in_sizes; (void)n_in; (void)out_size;
    static EncodeFn fn = nullptr;
    static uint32_t* act_base = nullptr;
    if (!fn) {
        cudaDriverEntryPointQueryResult st;
        cudaGetDriverEntryPoint("cuTensorMapEncodeTiled", (void**)&fn, cudaEnableDefault, &st);
        void* a = nullptr;
        cudaGetSymbolAddress(&a, g_act);
        act_base = (uint32_t*)(((uintptr_t)a + 0xFFFFF) & ~(uintptr_t)0xFFFFF);
        cudaFuncSetAttribute(fused_block_kernel, cudaFuncAttributeMaxDynamicSharedMemorySize, SMEM_BYTES);
    }
    Params p;
    p.x = (const bf16*)d_in[0];
    const bf16* wqkv = (const bf16*)d_in[1];
    p.wqkv = wqkv;
    p.wop = (const bf16*)d_in[2];
    p.wg = (const bf16*)d_in[4];
    p.wu = (const bf16*)d_in[5];
    p.wd = (const bf16*)d_in[6];
    p.c = (const bf16*)d_in[7];
    p.wmod = (const bf16*)d_in[8];
    p.out = (bf16*)d_out;
    p.zero = 0;
    p.actb = act_base;
    make_map(fn, &p.wm, p.wmod, 2688, 448, 1, 5376, 5376 * 448, 16, 224, 1, CU_TENSOR_MAP_SWIZZLE_NONE);
    make_map(fn, &p.wm2, p.wmod, 2688, 448, 1, 5376, 5376 * 448, 32, 224, 1, CU_TENSOR_MAP_SWIZZLE_NONE);
    make_map(fn, &p.om, p.out, 448, 2048, 1, 896, 896 * 2048, 56, 16, 1, CU_TENSOR_MAP_SWIZZLE_NONE);
    make_map(fn, &p.xm, p.x, 448, 2048, 1, 896, 896 * 2048, 64, 128, 1, CU_TENSOR_MAP_SWIZZLE_128B);
    make_map(fn, &p.qkv, wqkv, 1344, 448, 1, 2688, 2688 * 448, 64, 224, 1, CU_TENSOR_MAP_SWIZZLE_128B);
    make_map(fn, &p.wo, p.wop, 448, 448, 1, 896, 896 * 448, 64, 224, 1, CU_TENSOR_MAP_SWIZZLE_128B);
    make_map(fn, &p.ga, p.wg, 64, 448, 28, 3584, 128, 64, 32, 2, CU_TENSOR_MAP_SWIZZLE_128B);
    make_map(fn, &p.ua, p.wu, 64, 448, 28, 3584, 128, 64, 32, 2, CU_TENSOR_MAP_SWIZZLE_128B);
    make_map(fn, &p.gb, p.wg, 64, 448, 28, 3584, 128, 64, 64, 1, CU_TENSOR_MAP_SWIZZLE_128B);
    make_map(fn, &p.ub, p.wu, 64, 448, 28, 3584, 128, 64, 64, 1, CU_TENSOR_MAP_SWIZZLE_128B);
    make_map(fn, &p.gc, p.wg, 32, 448, 56, 3584, 64, 32, 64, 1, CU_TENSOR_MAP_SWIZZLE_64B);
    make_map(fn, &p.uc, p.wu, 32, 448, 56, 3584, 64, 32, 64, 1, CU_TENSOR_MAP_SWIZZLE_64B);
    make_map(fn, &p.dn, p.wd, 8, 1792, 56, 896, 16, 8, 32, 7, CU_TENSOR_MAP_SWIZZLE_NONE);
    fused_block_kernel<<<GRID, 384, SMEM_BYTES>>>(p);
}
```

```cpp
#include <cuda_runtime.h>
#include <cuda_bf16.h>
#include <cuda.h>
#include <stdint.h>

typedef __nv_bfloat16 bf16;

__device__ __forceinline__ void wgmma_rl_56(float* d, uint32_t a0, uint32_t a1, uint32_t a2, uint32_t a3, uint64_t db, int sd) {
  asm volatile("{\n.reg .pred p;\nsetp.ne.b32 p, %33, 0;\n"
    "wgmma.mma_async.sync.aligned.m64n56k16.f32.bf16.bf16 {%0,%1,%2,%3,%4,%5,%6,%7,%8,%9,%10,%11,%12,%13,%14,%15,%16,%17,%18,%19,%20,%21,%22,%23,%24,%25,%26,%27}, {%28,%29,%30,%31}, %32, p, 1, 1, 1;\n}\n"
    : "+f"(d[0]),"+f"(d[1]),"+f"(d[2]),"+f"(d[3]),"+f"(d[4]),"+f"(d[5]),"+f"(d[6]),"+f"(d[7]),"+f"(d[8]),"+f"(d[9]),"+f"(d[10]),"+f"(d[11]),"+f"(d[12]),"+f"(d[13]),"+f"(d[14]),"+f"(d[15]),"+f"(d[16]),"+f"(d[17]),"+f"(d[18]),"+f"(d[19]),"+f"(d[20]),"+f"(d[21]),"+f"(d[22]),"+f"(d[23]),"+f"(d[24]),"+f"(d[25]),"+f"(d[26]),"+f"(d[27])
    : "r"(a0), "r"(a1), "r"(a2), "r"(a3), "l"(db), "r"(sd));
}
template<uint64_t CA, uint64_t CB> __device__ __forceinline__ void wgmma_ss_56(float* d, uint32_t da, uint32_t db, int sd) {
  asm volatile("{\n.reg .pred p;\n.reg .b64 a, b;\nsetp.ne.b32 p, %30, 0;\nmov.b64 a, {%28, %31};\nmov.b64 b, {%29, %32};\n"
    "wgmma.mma_async.sync.aligned.m64n56k16.f32.bf16.bf16 {%0,%1,%2,%3,%4,%5,%6,%7,%8,%9,%10,%11,%12,%13,%14,%15,%16,%17,%18,%19,%20,%21,%22,%23,%24,%25,%26,%27}, a, b, p, 1, 1, 0, 1;\n}\n"
    : "+f"(d[0]),"+f"(d[1]),"+f"(d[2]),"+f"(d[3]),"+f"(d[4]),"+f"(d[5]),"+f"(d[6]),"+f"(d[7]),"+f"(d[8]),"+f"(d[9]),"+f"(d[10]),"+f"(d[11]),"+f"(d[12]),"+f"(d[13]),"+f"(d[14]),"+f"(d[15]),"+f"(d[16]),"+f"(d[17]),"+f"(d[18]),"+f"(d[19]),"+f"(d[20]),"+f"(d[21]),"+f"(d[22]),"+f"(d[23]),"+f"(d[24]),"+f"(d[25]),"+f"(d[26]),"+f"(d[27])
    : "r"(da), "r"(db), "r"(sd), "n"((uint32_t)(CA >> 32)), "n"((uint32_t)(CB >> 32)));
}
__device__ __forceinline__ void wgmma_rl_256(float* d, uint32_t a0, uint32_t a1, uint32_t a2, uint32_t a3, uint64_t db, int sd) {
  asm volatile("{\n.reg .pred p;\nsetp.ne.b32 p, %133, 0;\n"
    "wgmma.mma_async.sync.aligned.m64n256k16.f32.bf16.bf16 {%0,%1,%2,%3,%4,%5,%6,%7,%8,%9,%10,%11,%12,%13,%14,%15,%16,%17,%18,%19,%20,%21,%22,%23,%24,%25,%26,%27,%28,%29,%30,%31,%32,%33,%34,%35,%36,%37,%38,%39,%40,%41,%42,%43,%44,%45,%46,%47,%48,%49,%50,%51,%52,%53,%54,%55,%56,%57,%58,%59,%60,%61,%62,%63,%64,%65,%66,%67,%68,%69,%70,%71,%72,%73,%74,%75,%76,%77,%78,%79,%80,%81,%82,%83,%84,%85,%86,%87,%88,%89,%90,%91,%92,%93,%94,%95,%96,%97,%98,%99,%100,%101,%102,%103,%104,%105,%106,%107,%108,%109,%110,%111,%112,%113,%114,%115,%116,%117,%118,%119,%120,%121,%122,%123,%124,%125,%126,%127}, {%128,%129,%130,%131}, %132, p, 1, 1, 1;\n}\n"
    : "+f"(d[0]),"+f"(d[1]),"+f"(d[2]),"+f"(d[3]),"+f"(d[4]),"+f"(d[5]),"+f"(d[6]),"+f"(d[7]),"+f"(d[8]),"+f"(d[9]),"+f"(d[10]),"+f"(d[11]),"+f"(d[12]),"+f"(d[13]),"+f"(d[14]),"+f"(d[15]),"+f"(d[16]),"+f"(d[17]),"+f"(d[18]),"+f"(d[19]),"+f"(d[20]),"+f"(d[21]),"+f"(d[22]),"+f"(d[23]),"+f"(d[24]),"+f"(d[25]),"+f"(d[26]),"+f"(d[27]),"+f"(d[28]),"+f"(d[29]),"+f"(d[30]),"+f"(d[31]),"+f"(d[32]),"+f"(d[33]),"+f"(d[34]),"+f"(d[35]),"+f"(d[36]),"+f"(d[37]),"+f"(d[38]),"+f"(d[39]),"+f"(d[40]),"+f"(d[41]),"+f"(d[42]),"+f"(d[43]),"+f"(d[44]),"+f"(d[45]),"+f"(d[46]),"+f"(d[47]),"+f"(d[48]),"+f"(d[49]),"+f"(d[50]),"+f"(d[51]),"+f"(d[52]),"+f"(d[53]),"+f"(d[54]),"+f"(d[55]),"+f"(d[56]),"+f"(d[57]),"+f"(d[58]),"+f"(d[59]),"+f"(d[60]),"+f"(d[61]),"+f"(d[62]),"+f"(d[63]),"+f"(d[64]),"+f"(d[65]),"+f"(d[66]),"+f"(d[67]),"+f"(d[68]),"+f"(d[69]),"+f"(d[70]),"+f"(d[71]),"+f"(d[72]),"+f"(d[73]),"+f"(d[74]),"+f"(d[75]),"+f"(d[76]),"+f"(d[77]),"+f"(d[78]),"+f"(d[79]),"+f"(d[80]),"+f"(d[81]),"+f"(d[82]),"+f"(d[83]),"+f"(d[84]),"+f"(d[85]),"+f"(d[86]),"+f"(d[87]),"+f"(d[88]),"+f"(d[89]),"+f"(d[90]),"+f"(d[91]),"+f"(d[92]),"+f"(d[93]),"+f"(d[94]),"+f"(d[95]),"+f"(d[96]),"+f"(d[97]),"+f"(d[98]),"+f"(d[99]),"+f"(d[100]),"+f"(d[101]),"+f"(d[102]),"+f"(d[103]),"+f"(d[104]),"+f"(d[105]),"+f"(d[106]),"+f"(d[107]),"+f"(d[108]),"+f"(d[109]),"+f"(d[110]),"+f"(d[111]),"+f"(d[112]),"+f"(d[113]),"+f"(d[114]),"+f"(d[115]),"+f"(d[116]),"+f"(d[117]),"+f"(d[118]),"+f"(d[119]),"+f"(d[120]),"+f"(d[121]),"+f"(d[122]),"+f"(d[123]),"+f"(d[124]),"+f"(d[125]),"+f"(d[126]),"+f"(d[127])
    : "r"(a0), "r"(a1), "r"(a2), "r"(a3), "l"(db), "r"(sd));
}
template<uint64_t CA, uint64_t CB> __device__ __forceinline__ void wgmma_ss_128(float* d, uint32_t da, uint32_t db, int sd) {
  asm volatile("{\n.reg .pred p;\n.reg .b64 a, b;\nsetp.ne.b32 p, %66, 0;\nmov.b64 a, {%64, %67};\nmov.b64 b, {%65, %68};\n"
    "wgmma.mma_async.sync.aligned.m64n128k16.f32.bf16.bf16 {%0,%1,%2,%3,%4,%5,%6,%7,%8,%9,%10,%11,%12,%13,%14,%15,%16,%17,%18,%19,%20,%21,%22,%23,%24,%25,%26,%27,%28,%29,%30,%31,%32,%33,%34,%35,%36,%37,%38,%39,%40,%41,%42,%43,%44,%45,%46,%47,%48,%49,%50,%51,%52,%53,%54,%55,%56,%57,%58,%59,%60,%61,%62,%63}, a, b, p, 1, 1, 0, 1;\n}\n"
    : "+f"(d[0]),"+f"(d[1]),"+f"(d[2]),"+f"(d[3]),"+f"(d[4]),"+f"(d[5]),"+f"(d[6]),"+f"(d[7]),"+f"(d[8]),"+f"(d[9]),"+f"(d[10]),"+f"(d[11]),"+f"(d[12]),"+f"(d[13]),"+f"(d[14]),"+f"(d[15]),"+f"(d[16]),"+f"(d[17]),"+f"(d[18]),"+f"(d[19]),"+f"(d[20]),"+f"(d[21]),"+f"(d[22]),"+f"(d[23]),"+f"(d[24]),"+f"(d[25]),"+f"(d[26]),"+f"(d[27]),"+f"(d[28]),"+f"(d[29]),"+f"(d[30]),"+f"(d[31]),"+f"(d[32]),"+f"(d[33]),"+f"(d[34]),"+f"(d[35]),"+f"(d[36]),"+f"(d[37]),"+f"(d[38]),"+f"(d[39]),"+f"(d[40]),"+f"(d[41]),"+f"(d[42]),"+f"(d[43]),"+f"(d[44]),"+f"(d[45]),"+f"(d[46]),"+f"(d[47]),"+f"(d[48]),"+f"(d[49]),"+f"(d[50]),"+f"(d[51]),"+f"(d[52]),"+f"(d[53]),"+f"(d[54]),"+f"(d[55]),"+f"(d[56]),"+f"(d[57]),"+f"(d[58]),"+f"(d[59]),"+f"(d[60]),"+f"(d[61]),"+f"(d[62]),"+f"(d[63])
    : "r"(da), "r"(db), "r"(sd), "n"((uint32_t)(CA >> 32)), "n"((uint32_t)(CB >> 32)));
}
template<uint64_t CA, uint64_t CB> __device__ __forceinline__ void wgmma_ss_64(float* d, uint32_t da, uint32_t db, int sd) {
  asm volatile("{\n.reg .pred p;\n.reg .b64 a, b;\nsetp.ne.b32 p, %34, 0;\nmov.b64 a, {%32, %35};\nmov.b64 b, {%33, %36};\n"
    "wgmma.mma_async.sync.aligned.m64n64k16.f32.bf16.bf16 {%0,%1,%2,%3,%4,%5,%6,%7,%8,%9,%10,%11,%12,%13,%14,%15,%16,%17,%18,%19,%20,%21,%22,%23,%24,%25,%26,%27,%28,%29,%30,%31}, a, b, p, 1, 1, 0, 1;\n}\n"
    : "+f"(d[0]),"+f"(d[1]),"+f"(d[2]),"+f"(d[3]),"+f"(d[4]),"+f"(d[5]),"+f"(d[6]),"+f"(d[7]),"+f"(d[8]),"+f"(d[9]),"+f"(d[10]),"+f"(d[11]),"+f"(d[12]),"+f"(d[13]),"+f"(d[14]),"+f"(d[15]),"+f"(d[16]),"+f"(d[17]),"+f"(d[18]),"+f"(d[19]),"+f"(d[20]),"+f"(d[21]),"+f"(d[22]),"+f"(d[23]),"+f"(d[24]),"+f"(d[25]),"+f"(d[26]),"+f"(d[27]),"+f"(d[28]),"+f"(d[29]),"+f"(d[30]),"+f"(d[31])
    : "r"(da), "r"(db), "r"(sd), "n"((uint32_t)(CA >> 32)), "n"((uint32_t)(CB >> 32)));
}
template<uint64_t CA, uint64_t CB> __device__ __forceinline__ void wgmma_ss_112(float* d, uint32_t da, uint32_t db, int sd) {
  asm volatile("{\n.reg .pred p;\n.reg .b64 a, b;\nsetp.ne.b32 p, %58, 0;\nmov.b64 a, {%56, %59};\nmov.b64 b, {%57, %60};\n"
    "wgmma.mma_async.sync.aligned.m64n112k16.f32.bf16.bf16 {%0,%1,%2,%3,%4,%5,%6,%7,%8,%9,%10,%11,%12,%13,%14,%15,%16,%17,%18,%19,%20,%21,%22,%23,%24,%25,%26,%27,%28,%29,%30,%31,%32,%33,%34,%35,%36,%37,%38,%39,%40,%41,%42,%43,%44,%45,%46,%47,%48,%49,%50,%51,%52,%53,%54,%55}, a, b, p, 1, 1, 0, 1;\n}\n"
    : "+f"(d[0]),"+f"(d[1]),"+f"(d[2]),"+f"(d[3]),"+f"(d[4]),"+f"(d[5]),"+f"(d[6]),"+f"(d[7]),"+f"(d[8]),"+f"(d[9]),"+f"(d[10]),"+f"(d[11]),"+f"(d[12]),"+f"(d[13]),"+f"(d[14]),"+f"(d[15]),"+f"(d[16]),"+f"(d[17]),"+f"(d[18]),"+f"(d[19]),"+f"(d[20]),"+f"(d[21]),"+f"(d[22]),"+f"(d[23]),"+f"(d[24]),"+f"(d[25]),"+f"(d[26]),"+f"(d[27]),"+f"(d[28]),"+f"(d[29]),"+f"(d[30]),"+f"(d[31]),"+f"(d[32]),"+f"(d[33]),"+f"(d[34]),"+f"(d[35]),"+f"(d[36]),"+f"(d[37]),"+f"(d[38]),"+f"(d[39]),"+f"(d[40]),"+f"(d[41]),"+f"(d[42]),"+f"(d[43]),"+f"(d[44]),"+f"(d[45]),"+f"(d[46]),"+f"(d[47]),"+f"(d[48]),"+f"(d[49]),"+f"(d[50]),"+f"(d[51]),"+f"(d[52]),"+f"(d[53]),"+f"(d[54]),"+f"(d[55])
    : "r"(da), "r"(db), "r"(sd), "n"((uint32_t)(CA >> 32)), "n"((uint32_t)(CB >> 32)));
}
__device__ __forceinline__ void wgmma_rl_112(float* d, uint32_t a0, uint32_t a1, uint32_t a2, uint32_t a3, uint64_t db, int sd) {
  asm volatile("{\n.reg .pred p;\nsetp.ne.b32 p, %61, 0;\n"
    "wgmma.mma_async.sync.aligned.m64n112k16.f32.bf16.bf16 {%0,%1,%2,%3,%4,%5,%6,%7,%8,%9,%10,%11,%12,%13,%14,%15,%16,%17,%18,%19,%20,%21,%22,%23,%24,%25,%26,%27,%28,%29,%30,%31,%32,%33,%34,%35,%36,%37,%38,%39,%40,%41,%42,%43,%44,%45,%46,%47,%48,%49,%50,%51,%52,%53,%54,%55}, {%56,%57,%58,%59}, %60, p, 1, 1, 1;\n}\n"
    : "+f"(d[0]),"+f"(d[1]),"+f"(d[2]),"+f"(d[3]),"+f"(d[4]),"+f"(d[5]),"+f"(d[6]),"+f"(d[7]),"+f"(d[8]),"+f"(d[9]),"+f"(d[10]),"+f"(d[11]),"+f"(d[12]),"+f"(d[13]),"+f"(d[14]),"+f"(d[15]),"+f"(d[16]),"+f"(d[17]),"+f"(d[18]),"+f"(d[19]),"+f"(d[20]),"+f"(d[21]),"+f"(d[22]),"+f"(d[23]),"+f"(d[24]),"+f"(d[25]),"+f"(d[26]),"+f"(d[27]),"+f"(d[28]),"+f"(d[29]),"+f"(d[30]),"+f"(d[31]),"+f"(d[32]),"+f"(d[33]),"+f"(d[34]),"+f"(d[35]),"+f"(d[36]),"+f"(d[37]),"+f"(d[38]),"+f"(d[39]),"+f"(d[40]),"+f"(d[41]),"+f"(d[42]),"+f"(d[43]),"+f"(d[44]),"+f"(d[45]),"+f"(d[46]),"+f"(d[47]),"+f"(d[48]),"+f"(d[49]),"+f"(d[50]),"+f"(d[51]),"+f"(d[52]),"+f"(d[53]),"+f"(d[54]),"+f"(d[55])
    : "r"(a0), "r"(a1), "r"(a2), "r"(a3), "l"(db), "r"(sd));
}

constexpr int DM = 448;
constexpr int NCTA = 128;
#define MAPPING 1
#define GRID 128
#define PINGPONG 0
#define WIN 6
#define WIN_END 25
#define UNR_B 1
#define UNR_C 1
constexpr int kB = UNR_B, kC = UNR_C;
#define LIKELY(x) __builtin_expect(!!(x), 1)
#define PACE 1
#define PACE_END 6
#define GEMV_AT 1
#define NPRE 14
#define ATT_OFF 0
#define ATT_WG 1
#define XFIRST 7
#define KDELAY -1
#define KEARLY 0
#define MAP_S 4
constexpr int SPIN_LIMIT = 1 << 22;

constexpr uint32_t OFF_X = 0, OFF_Y = 114688, OFF_MISC = 229376, SMEM_BYTES = 232448;
constexpr uint32_t Y_VR = 0, Y_K = 28672, Y_KOWN = 57344, Y_VOWN = 71680, Y_Q = 86016;
constexpr uint32_t HALF = 57344;
constexpr uint32_t X_STAT = 49152;
constexpr uint32_t OUT_STAGE = 16384;
constexpr uint32_t M_BAR = OFF_MISC;
constexpr uint32_t M_ST = OFF_MISC + 512;
constexpr uint32_t M_G = OFF_MISC + 2304;
constexpr uint32_t M_EPOCH = OFF_MISC + 3040;
enum { B_XFULL = 0, B_FULLK = 7, B_FULLV = 8, B_FULLQ, B_KRFULL, B_VRFULL, B_WOFULL, B_XCH, B_MOD1 = 15, B_FULL = 16, B_WMFULL = 30,
       B_EMPTY = 32, B_XFREE = B_EMPTY + 12, B_GEMV, B_PEER,
       B_PUB = 47,
       B_WMFREE = 56, B_HRDY, B_GFULL = B_HRDY + 3, B_DONE = 31, B_DUMMY = B_GEMV };

__device__ uint32_t g_ticket;
__device__ __align__(128) uint32_t g_mod[8 * 6 * DM];
__device__ __align__(128) uint32_t g_flag[144 * 128];
constexpr int RB_WORDS = 262144, RB_KV = 0, RB_O = 57344, RB_X1 = 86016, RB_H2 = 143360, RB_ST = 258048;
__device__ __align__(128) uint32_t g_act[18 * RB_WORDS];
__device__ __align__(128) uint32_t g_wd[56 * 4 * 1792];
#define PROFH(id)
#define PROFH1(id)
#define PROFC(id)

struct alignas(64) Params {
    CUtensorMap wm, wm2, om, xm, qkv, wo, ga, ua, gb, ub, gc, uc, dn;
    const bf16 *x, *c, *wqkv, *wmod, *wg, *wu, *wd, *wop;
    bf16* out;
    uint32_t* actb;
    uint32_t zero;
};

__device__ __forceinline__ void mbar_init(uint32_t bar, int cnt) { asm volatile("mbarrier.init.shared::cta.b64 [%0], %1;" ::"r"(bar), "r"(cnt) : "memory"); }
__device__ __forceinline__ void mbar_expect_tx(uint32_t bar, uint32_t bytes) { asm volatile("mbarrier.arrive.expect_tx.shared::cta.b64 _, [%0], %1;" ::"r"(bar), "r"(bytes) : "memory"); }
__device__ __forceinline__ void mbar_arrive(uint32_t bar) { asm volatile("mbarrier.arrive.shared::cta.b64 _, [%0];" ::"r"(bar) : "memory"); }
__device__ __forceinline__ void mbar_wait(uint32_t bar, uint32_t parity) {
    uint32_t ok; int n = 0;
    do {
        asm volatile("{\n.reg .pred p;\nmbarrier.try_wait.parity.shared::cta.b64 p, [%1], %2;\nselp.u32 %0, 1, 0, p;\n}" : "=r"(ok) : "r"(bar), "r"(parity) : "memory");
        if (++n > SPIN_LIMIT) __trap();
    } while (!ok);
}
__device__ __forceinline__ void mbar_wait_c(uint32_t bar, uint32_t parity) {
    asm volatile("{\n.reg .pred p;\nWL:\nmbarrier.try_wait.parity.shared::cta.b64 p, [%0], %1, 0x989680;\n@!p bra WL;\n}" ::"r"(bar), "r"(parity) : "memory");
}
__device__ __forceinline__ void mbar_wait_cluster(uint32_t bar, uint32_t parity) {
    asm volatile("{\n.reg .pred p;\nWL:\nmbarrier.try_wait.parity.acquire.cluster.shared::cta.b64 p, [%0], %1, 0x989680;\n@!p bra WL;\n}" ::"r"(bar), "r"(parity) : "memory");
}
__device__ __forceinline__ void warp_arrive(uint32_t bar) {
    __syncwarp();
    asm volatile("{\n.reg .pred p;\nelect.sync _|p, 0xffffffff;\n@p mbarrier.arrive.shared::cta.b64 _, [%0];\n}" ::"r"(bar) : "memory");
}
__device__ __forceinline__ int opaque(int v) { return __shfl_sync(~0u, v, 0); }
__device__ __forceinline__ int fresh_tid() { int v; asm volatile("mov.u32 %0, %%tid.x;" : "=r"(v)); return v; }
__device__ __forceinline__ void bar_sync(int id, int n) { asm volatile("bar.sync %0, %1;" ::"r"(id), "r"(n) : "memory"); }
__device__ __forceinline__ void bar_arrive(int id, int n) { asm volatile("bar.arrive %0, %1;" ::"r"(id), "r"(n) : "memory"); }
__device__ __forceinline__ void fence_async_smem() { asm volatile("fence.proxy.async.shared::cta;" ::: "memory"); }
__device__ __forceinline__ void fence_async_global() { asm volatile("fence.proxy.async.global;" ::: "memory"); }
__device__ __forceinline__ void fence_gpu() { asm volatile("fence.release.gpu;" ::: "memory"); }
__device__ __forceinline__ void tma3(uint32_t dst, const CUtensorMap* m, int c0, int c1, int c2, uint32_t bar) {
    asm volatile("cp.async.bulk.tensor.3d.shared::cluster.global.mbarrier::complete_tx::bytes [%0], [%1, {%3, %4, %5}], [%2];"
                 ::"r"(dst), "l"(m), "r"(bar), "r"(c0), "r"(c1), "r"(c2) : "memory");
}
__device__ __forceinline__ void bulk_load(uint32_t dst, const void* src, uint32_t bytes, uint32_t bar) {
    asm volatile("cp.async.bulk.shared::cluster.global.mbarrier::complete_tx::bytes [%0], [%1], %2, [%3];" ::"r"(dst), "l"(src), "r"(bytes), "r"(bar) : "memory");
}
__device__ __forceinline__ void expect_e(uint32_t bar, uint32_t bytes) {
    asm volatile("{\n.reg .pred p;\nelect.sync _|p, 0xffffffff;\n@p mbarrier.arrive.expect_tx.shared::cta.b64 _, [%0], %1;\n}" ::"r"(bar), "r"(bytes) : "memory");
}
__device__ __forceinline__ void tma3_e(uint32_t dst, const CUtensorMap* m, int c0, int c1, int c2, uint32_t bar) {
    asm volatile("{\n.reg .pred p;\nelect.sync _|p, 0xffffffff;\n@p cp.async.bulk.tensor.3d.shared::cluster.global.mbarrier::complete_tx::bytes [%0], [%1, {%3, %4, %5}], [%2];\n}"
                 ::"r"(dst), "l"(m), "r"(bar), "r"(c0), "r"(c1), "r"(c2) : "memory");
}
__device__ __forceinline__ void bulk_e(uint32_t dst, const void* src, uint32_t bytes, uint32_t bar) {
    asm volatile("{\n.reg .pred p;\nelect.sync _|p, 0xffffffff;\n@p cp.async.bulk.shared::cluster.global.mbarrier::complete_tx::bytes [%0], [%1], %2, [%3];\n}"
                 ::"r"(dst), "l"(src), "r"(bytes), "r"(bar) : "memory");
}
__device__ __forceinline__ void init_e(uint32_t bar, int cnt) {
    asm volatile("{\n.reg .pred p;\nelect.sync _|p, 0xffffffff;\n@p mbarrier.init.shared::cta.b64 [%0], %1;\n}" ::"r"(bar), "r"(cnt) : "memory");
}
__device__ __forceinline__ void l2_prefetch_e(const void* src, uint32_t bytes) {
    asm volatile("{\n.reg .pred p;\nelect.sync _|p, 0xffffffff;\n@p cp.async.bulk.prefetch.L2.global [%0], %1;\n}" ::"l"(src), "r"(bytes) : "memory");
}
__device__ __forceinline__ uint32_t ld_relaxed(const uint32_t* p) { uint32_t v; asm volatile("ld.relaxed.gpu.global.u32 %0, [%1];" : "=r"(v) : "l"(p) : "memory"); return v; }
__device__ __forceinline__ void st_relaxed(uint32_t* p, uint32_t v) { asm volatile("st.relaxed.gpu.global.u32 [%0], %1;" ::"l"(p), "r"(v) : "memory"); }
__device__ __forceinline__ uint4 ld_relaxed4(const uint4* p) { uint4 v; asm volatile("ld.relaxed.gpu.global.v4.u32 {%0,%1,%2,%3}, [%4];" : "=r"(v.x), "=r"(v.y), "=r"(v.z), "=r"(v.w) : "l"(p) : "memory"); return v; }
__device__ __forceinline__ void st_relaxed4(uint4* p, uint4 v) { asm volatile("st.relaxed.gpu.global.v4.u32 [%0], {%1,%2,%3,%4};" ::"l"(p), "r"(v.x), "r"(v.y), "r"(v.z), "r"(v.w) : "memory"); }
__device__ __forceinline__ uint4 ldg_nc4(const void* p) { uint4 v; asm volatile("ld.global.nc.L1::no_allocate.v4.u32 {%0,%1,%2,%3}, [%4];" : "=r"(v.x), "=r"(v.y), "=r"(v.z), "=r"(v.w) : "l"(p)); return v; }
__device__ __forceinline__ uint32_t ldg_nc(const void* p) { uint32_t v; asm volatile("ld.global.nc.u32 %0, [%1];" : "=r"(v) : "l"(p)); return v; }
__device__ __forceinline__ uint32_t ld_acquire(const uint32_t* p) { uint32_t v; asm volatile("ld.acquire.gpu.global.u32 %0, [%1];" : "=r"(v) : "l"(p) : "memory"); return v; }
__device__ __forceinline__ uint4 lds4(uint32_t a) { uint4 v; asm volatile("ld.shared.v4.u32 {%0,%1,%2,%3}, [%4];" : "=r"(v.x), "=r"(v.y), "=r"(v.z), "=r"(v.w) : "r"(a) : "memory"); return v; }
__device__ __forceinline__ float2 lds2f(uint32_t a) { float2 v; asm volatile("ld.shared.v2.f32 {%0,%1}, [%2];" : "=f"(v.x), "=f"(v.y) : "r"(a) : "memory"); return v; }
__device__ __forceinline__ uint32_t lds1(uint32_t a) { uint32_t v; asm volatile("ld.shared.u32 %0, [%1];" : "=r"(v) : "r"(a) : "memory"); return v; }
__device__ __forceinline__ void sts4(uint32_t a, uint4 v) { asm volatile("st.shared.v4.u32 [%0], {%1,%2,%3,%4};" ::"r"(a), "r"(v.x), "r"(v.y), "r"(v.z), "r"(v.w) : "memory"); }
__device__ __forceinline__ void sts2(uint32_t a, uint32_t x, uint32_t y) { asm volatile("st.shared.v2.u32 [%0], {%1,%2};" ::"r"(a), "r"(x), "r"(y) : "memory"); }
__device__ __forceinline__ void sts1(uint32_t a, uint32_t v) { asm volatile("st.shared.u32 [%0], %1;" ::"r"(a), "r"(v) : "memory"); }
__device__ __forceinline__ void stsm4(uint32_t a, uint32_t r0, uint32_t r1, uint32_t r2, uint32_t r3) {
    asm volatile("stmatrix.sync.aligned.m8n8.x4.shared.b16 [%0], {%1,%2,%3,%4};" ::"r"(a), "r"(r0), "r"(r1), "r"(r2), "r"(r3));
}
__device__ __forceinline__ uint32_t pack2(float lo, float hi) { uint32_t r; asm("cvt.rn.bf16x2.f32 %0, %1, %2;" : "=r"(r) : "f"(hi), "f"(lo)); return r; }
__device__ __forceinline__ uint32_t pack2_relu(float lo, float hi) { uint32_t r; asm("cvt.rn.relu.bf16x2.f32 %0, %1, %2;" : "=r"(r) : "f"(hi), "f"(lo)); return r; }
__device__ __forceinline__ uint32_t hfma2(uint32_t a, uint32_t b, uint32_t c) { uint32_t r; asm("fma.rn.bf16x2 %0, %1, %2, %3;" : "=r"(r) : "r"(a), "r"(b), "r"(c)); return r; }
__device__ __forceinline__ uint32_t hmul2(uint32_t a, uint32_t b) { uint32_t r; asm("mul.rn.bf16x2 %0, %1, %2;" : "=r"(r) : "r"(a), "r"(b)); return r; }
__device__ __forceinline__ float bf_lo(uint32_t v) { return __uint_as_float(v << 16); }
__device__ __forceinline__ float bf_hi(uint32_t v) { return __uint_as_float(v & 0xFFFF0000u); }
__device__ __forceinline__ float bf_round(float v) { return bf_lo(pack2(v, 0.f)); }
__device__ __forceinline__ float ex2(float x) { float r; asm("ex2.approx.ftz.f32 %0, %1;" : "=f"(r) : "f"(x)); return r; }
__device__ __forceinline__ void mma16816(float* d, uint32_t a0, uint32_t a1, uint32_t a2, uint32_t a3, uint32_t b0, uint32_t b1) {
    asm("mma.sync.aligned.m16n8k16.row.col.f32.bf16.bf16.f32 {%0,%1,%2,%3}, {%4,%5,%6,%7}, {%8,%9}, {%0,%1,%2,%3};"
        : "+f"(d[0]), "+f"(d[1]), "+f"(d[2]), "+f"(d[3]) : "r"(a0), "r"(a1), "r"(a2), "r"(a3), "r"(b0), "r"(b1));
}
__device__ __forceinline__ void mma16816_first(float* d, uint32_t a0, uint32_t a1, uint32_t a2, uint32_t a3, uint32_t b0, uint32_t b1) {
    asm volatile("mma.sync.aligned.m16n8k16.row.col.f32.bf16.bf16.f32 {%0,%1,%2,%3}, {%4,%5,%6,%7}, {%8,%9}, {%10,%10,%10,%10};"
        : "=f"(d[0]), "=f"(d[1]), "=f"(d[2]), "=f"(d[3]) : "r"(a0), "r"(a1), "r"(a2), "r"(a3), "r"(b0), "r"(b1), "f"(0.f));
}
__device__ __forceinline__ void mma16816_v(float* d, uint32_t a0, uint32_t a1, uint32_t a2, uint32_t a3, uint32_t b0, uint32_t b1) {
    asm volatile("mma.sync.aligned.m16n8k16.row.col.f32.bf16.bf16.f32 {%0,%1,%2,%3}, {%4,%5,%6,%7}, {%8,%9}, {%0,%1,%2,%3};"
        : "+f"(d[0]), "+f"(d[1]), "+f"(d[2]), "+f"(d[3]) : "r"(a0), "r"(a1), "r"(a2), "r"(a3), "r"(b0), "r"(b1));
}
__device__ __forceinline__ void mma1688(float* d, uint32_t a0, uint32_t a1, uint32_t b0) {
    asm("mma.sync.aligned.m16n8k8.row.col.f32.bf16.bf16.f32 {%0,%1,%2,%3}, {%4,%5}, {%6}, {%0,%1,%2,%3};"
        : "+f"(d[0]), "+f"(d[1]), "+f"(d[2]), "+f"(d[3]) : "r"(a0), "r"(a1), "r"(b0));
}
__device__ __forceinline__ void ldsm4(uint32_t a, uint32_t* r) {
    asm volatile("ldmatrix.sync.aligned.m8n8.x4.shared.b16 {%0,%1,%2,%3}, [%4];" : "=r"(r[0]), "=r"(r[1]), "=r"(r[2]), "=r"(r[3]) : "r"(a));
}
__device__ __forceinline__ void ldsm4t(uint32_t a, uint32_t* r) {
    asm volatile("ldmatrix.sync.aligned.m8n8.x4.trans.shared.b16 {%0,%1,%2,%3}, [%4];" : "=r"(r[0]), "=r"(r[1]), "=r"(r[2]), "=r"(r[3]) : "r"(a));
}
__device__ __forceinline__ uint32_t nz(uint32_t v) { uint32_t r; asm("max.u32 %0, %1, 1;" : "=r"(r) : "r"(v)); return r; }
__device__ __forceinline__ float rcp(float x) { float r; asm("rcp.approx.ftz.f32 %0, %1;" : "=f"(r) : "f"(x)); return r; }
__device__ __forceinline__ uint2 ld_relaxed2(const void* p) { uint2 v; asm volatile("ld.relaxed.gpu.global.v2.u32 {%0,%1}, [%2];" : "=r"(v.x), "=r"(v.y) : "l"(p) : "memory"); return v; }
__device__ __forceinline__ void st_relaxed2(void* p, uint32_t x, uint32_t y) { asm volatile("st.relaxed.gpu.global.v2.u32 [%0], {%1,%2};" ::"l"(p), "r"(max(x, 1u)), "r"(max(y, 1u)) : "memory"); }
__host__ __device__ constexpr uint64_t dconst(uint32_t lbo, uint32_t sbo, uint32_t swz) {
    return ((uint64_t)(lbo >> 4) << 16) | ((uint64_t)(sbo >> 4) << 32) | ((uint64_t)swz << 62);
}
__device__ __forceinline__ uint32_t mkdesc(uint32_t addr, uint64_t c) { return (uint32_t)c | ((addr & 0x3FFFF) >> 4); }
#define WG_FENCE() asm volatile("wgmma.fence.sync.aligned;" ::: "memory")
#define WG_COMMIT() asm volatile("wgmma.commit_group.sync.aligned;" ::: "memory")
#define WG_WAIT(n) asm volatile("wgmma.wait_group.sync.aligned %0;" ::"n"(n) : "memory")
template <int N> __device__ __forceinline__ void reg_fence(float* d) {
#pragma unroll
    for (int i = 0; i < N; i++) asm volatile("" : "+f"(d[i])::"memory");
}
template <int N> __device__ __forceinline__ void reg_def(float* d) {
#pragma unroll
    for (int i = 0; i < N; i++) asm volatile("" : "=f"(d[i]));
}
template <int N> __device__ __forceinline__ void reg_def(uint32_t* d) {
#pragma unroll
    for (int i = 0; i < N; i++) asm volatile("" : "=r"(d[i]));
}
__device__ __forceinline__ bool is_unset(uint4 v) { return min(min(v.x, v.y), min(v.z, v.w)) == 0u; }
__device__ __forceinline__ uint4 nz4(uint32_t a, uint32_t b, uint32_t c, uint32_t d) { return make_uint4(max(a, 1u), max(b, 1u), max(c, 1u), max(d, 1u)); }
__device__ __forceinline__ void wait_flags(const uint32_t* p, uint32_t target, uint32_t mask) {
    int n = 0;
    while (~__ballot_sync(~0u, (int)(ld_relaxed(p) - target) >= 0) & mask) { if (++n > SPIN_LIMIT) __trap(); }
    asm volatile("fence.acquire.gpu;" ::: "memory");
}
__device__ __forceinline__ float silu_bf(uint32_t cbits) {
    const float c = __uint_as_float(cbits << 16);
    return bf_round(__fdividef(c, 1.f + fminf(ex2(-1.4426950408889634f * c), 1e30f)));
}
__device__ __forceinline__ void gemv_part(uint32_t wmbuf, int wp, int lane) {
    const uint32_t wa = wmbuf + wp * 512 + (8 * (lane >> 4) + (lane & 7)) * 32 + ((lane >> 3) & 1) * 16;
    float d[4] = {};
#pragma unroll
    for (int i = 0; i < 4; i++) {
        uint32_t A[4];
        const float2 v = lds2f(wmbuf + 28672 + (wp + 8 * i) * 32 + (lane & 3) * 8);
        ldsm4t(wa + (i < 3 || wp < 4 ? i : 0) * 4096, A);
        mma16816(d, A[0], A[1], A[2], A[3], __float_as_uint(v.x), __float_as_uint(v.y));
    }
    if ((lane & 3) == 0) {
        sts1(wmbuf + 29696 + (wp * 16 + (lane >> 2)) * 4, __float_as_uint(d[0]));
        sts1(wmbuf + 29696 + (wp * 16 + 8 + (lane >> 2)) * 4, __float_as_uint(d[2]));
    }
}
__device__ __forceinline__ uint32_t mod_word(float v, int col, uint32_t target) {
    v = bf_round(v);
    if ((col >= DM && col < 2 * DM) || (col >= 4 * DM && col < 5 * DM)) v += 1.f;
    return (pack2(v, 0.f) << 16) | (target & 0xFFFFu);
}
__device__ __forceinline__ const uint4* mod_src(int i, int r, int j, bool p2) {
    i = min(i, p2 ? 251 : 223);
    return (const uint4*)g_mod + (r & 7) * (6 * DM / 4) + (i < 224 ? (p2 ? 336 : 0) + i : (i < 238 ? 14 * j + i : 14 * j + i + 322));
}
__device__ __forceinline__ void mod_store(uint32_t sb, uint4 v, const uint4* src, int i) {
    const uint32_t tag = lds1(sb + M_EPOCH) + 1;
    while (__any_sync(~0u, (((v.x ^ tag) | (v.y ^ tag) | (v.z ^ tag) | (v.w ^ tag)) & 0xFFFFu) != 0u)) v = ld_relaxed4(src);
    if (i < 224) {
        const int isc = i >= 112, c4 = i - 112 * isc;
        const uint32_t a = sb + M_ST + (c4 >> 2) * 64 + (c4 & 1) * 32 + (c4 & 2) * 4 + (isc ? 0 : 4);
        sts1(a, __byte_perm(v.x, v.y, 0x7632));
        sts1(a + 16, __byte_perm(v.z, v.w, 0x7632));
    } else if (i < 252) {
        sts4(sb + M_G + (i - 224) * 16, make_uint4(v.x & 0xFFFF0000u, v.y & 0xFFFF0000u, v.z & 0xFFFF0000u, v.w & 0xFFFF0000u));
    }
}
__device__ __forceinline__ int pass_f(int fs, int ps) { return 224 * fs + ((fs & 1) ? (ps == 0 ? 96 : ps == 1 ? 32 : 0) : (ps == 0 ? 0 : ps == 1 ? 128 : 192)); }
__device__ __forceinline__ constexpr uint32_t slot_off(int l) { return l * 16384; }
__device__ __forceinline__ constexpr int g1_slot(int s) { return s % 7; }
__device__ __noinline__ void x1_fix(const uint32_t* g, uint32_t sa, int s) {
#pragma unroll 1
    for (int k = 4 * s; k < 4 * s + 4;) {
        const uint4 v = ld_relaxed4((const uint4*)(g + k * 256));
        sts4(sa + k * 1024, v);
        k += 2 * __all_sync(~0u, min(min(v.x, v.y), min(v.z, v.w)) != 0u);
    }
    __syncwarp();
}
__device__ __forceinline__ void ln_coeffs(float mean, float msq, uint32_t& r2, uint32_t& n2) {
    const float rs = bf_round(rsqrtf(fmaxf(msq - mean * mean, 0.f) + 1e-5f));
    r2 = pack2(rs, rs);
    n2 = pack2(-mean * rs, -mean * rs);
}

#define LOADW bulk_e(dst, g_wd + (size_t)((f >> 5) * 4 + nq) * 1792, 7168, bar);
template <int sec> __device__ __forceinline__ void ring_loader(const Params& p, uint32_t sb_, int r_, int j_, int lane) {
    const uint32_t sb = opaque(sb_);
    const int r = opaque(r_), j = opaque(j_), nq = j >> 1, fs = 4 * (j & 1) + nq;
    const int fa = pass_f(fs, 0), fb = pass_f(fs, 1), fc = pass_f(fs, 2);
    const uint32_t* h2src = (const uint32_t*)__shfl_sync(~0u, (unsigned long long)(p.actb + (size_t)r * RB_WORDS + RB_H2), 0);
    const CUtensorMap* gmap = (const CUtensorMap*)__shfl_sync(~0u, (unsigned long long)(&p.ga + sec), 0);
#define BAR(i) (sb + M_BAR + 8 * (i))
#define kh (j & 1)
            int sl = 0;
#pragma unroll 1
            for (int s = 0; s < 28; s++) {
                if (s == 7) { wait_flags(g_flag + (8 * r + j) * 128 + 96 + lane, lds1(sb + M_EPOCH) + 1, 0xFFFFu); fence_async_global(); }
                const int ps = s < 14 ? 0 : s < 21 ? 1 : 2;
                const uint32_t half = ps < 2 ? 8192 : 4096;
                const int sp = sl;
                if (s >= PACE && s < PACE_END) mbar_wait(BAR(B_FULL + s - PACE), 0);
                mbar_wait(BAR(B_EMPTY + sp), (s >= 7 && s < 14) || s >= 21);
                expect_e(BAR(B_FULL + sp), half);
                tma3_e(sb + slot_off(sp) + sec * half, gmap + 2 * ps, 0, ps ? 64 * sl : 32 * s, ps == 0 ? fa >> 6 : ps == 1 ? fb >> 6 : fc >> 5, BAR(B_FULL + sp));
                sl = sl == 6 ? 0 : sl + 1;
            }
            if (!sec) PROFH(3);
#pragma unroll 1
            for (int e = 0; e < 4; e++) {
                const uint32_t dst = sb + slot_off(e) + sec * 8192, bar = BAR(B_FULL + e);
                const int f = (e < 2 ? fa + 64 * e : e == 2 ? fb : fc) + 32 * sec;
                mbar_wait(BAR(B_EMPTY + e), 0);
                expect_e(bar, e == 3 && sec ? 0 : 7168);
                if (!(e == 3 && sec)) { LOADW }
            }
            sl = 4;
            int e = 4;
#pragma unroll 1
            for (int grp = 0; grp < 9; grp++) {
                const int ps = grp >= 6 ? 2 : grp >= 3 ? 1 : 0;
                int sidx = grp - 3 * ps;
                if (sec && sidx == 0) { mbar_wait(BAR(B_HRDY + ps), 0); fence_async_global(); }
                sidx += sidx >= nq;
                int f = pass_f(4 * kh + sidx, ps);
#pragma unroll 1
                for (int k = 4 >> ps; k > 0; k--, e++, f += 32) {
                    const uint32_t dst = sb + slot_off(sl), bar = BAR(B_FULL + sl);
                    mbar_wait(BAR(B_EMPTY + sl), e >= 12 && e < 24);
                    if (e < WIN_END && e >= WIN) mbar_wait(BAR(B_FULL + (sl >= WIN ? sl - WIN : sl + 12 - WIN)), e - WIN >= 12);
                    expect_e(bar, sec ? 8192 : 7168);
                    if (!sec) { LOADW }
                    else bulk_e(dst + 8192, h2src + f * 64, 8192, bar);
                    sl = sl == 11 ? 0 : sl + 1;
                }
            }
            if (!sec) PROFH(4);
}

#define PROF_PARAMS
#define PROF_ARGS
__device__ __noinline__ void helper_late(const Params& p, int r_, int j_, int warp_ PROF_PARAMS) {
    extern __shared__ __align__(1024) unsigned char smem[];
    const uint32_t sb = (uint32_t)__cvta_generic_to_shared(smem);
    const int r = opaque(r_), j = opaque(j_), warp = opaque(warp_), nq = j >> 1, b = 8 * r + j;
    uint32_t* const act = (uint32_t*)__shfl_sync(~0u, (unsigned long long)(p.actb + (size_t)r * RB_WORDS), 0);
    {
        const int lane = fresh_tid() & 31;
        const uint32_t target = lds1(sb + M_EPOCH) + 1;
        if (warp == 8) { expect_e(BAR(B_XCH), 14336); expect_e(BAR(B_XCH + 1), 14336); }
            if (warp == 9) {
#pragma unroll 1
                for (int kv = 0; kv < 2; kv++) {
                    mbar_wait(BAR(B_PUB + kv), 0);
                    wait_flags(g_flag + b * 128 + lane, target, (r >= 2 ? 6u : r == 1 ? 2u : 0u) << (8 * kv));
                    fence_async_global();
                    const uint32_t dst = sb + OFF_Y + (kv ? Y_VR : Y_K);
                    expect_e(BAR(B_KRFULL + kv), r >= 2 ? 28672 : r == 1 ? 14336 : 0);
                    if (r >= 2) bulk_e(dst, act - 2 * RB_WORDS + RB_KV + j * 7168 + kv * 3584, 14336, BAR(B_KRFULL + kv));
                    if (r >= 1) bulk_e(dst + 14336, act - RB_WORDS + RB_KV + j * 7168 + kv * 3584, 14336, BAR(B_KRFULL + kv));
                }
            } else if (warp == 8) {
                uint4 v[8];
                mbar_wait(BAR(B_WOFULL), 0);
#pragma unroll
                for (int k = 0; k < 8; k++) v[k] = ld_relaxed4(mod_src(lane + 32 * k, r, j, true));
#pragma unroll
                for (int k = 0; k < 8; k++) mod_store(sb, v[k], mod_src(lane + 32 * k, r, j, true), lane + 32 * k);
                warp_arrive(BAR(B_MOD1));
            } else if (warp == 11) {
                if (kh == 1 && r < 14) {
                    const uint32_t wmbuf = sb + OFF_X + HALF;
                    const int mcol = 2 * DM + 32 * (4 * r + nq);
                    mbar_wait(BAR(B_XFREE), 0);
                    tma3_e(wmbuf, &p.wm2, mcol, 0, 0, BAR(B_WMFULL));
                    tma3_e(wmbuf + 14336, &p.wm2, mcol, 224, 0, BAR(B_WMFULL));
#pragma unroll 1
                    for (int wd = lane; wd < 224; wd += 32) {
                        const uint32_t cb = __ldg((const uint32_t*)p.c + wd);
                        sts1(wmbuf + 28672 + (wd >> 3) * 32 + (wd & 3) * 8 + (wd & 4), pack2(silu_bf(cb & 0xFFFFu), silu_bf(cb >> 16)));
                    }
                    __syncwarp();
                    mbar_wait(BAR(B_WMFULL), 0);
                    const uint32_t wa = wmbuf + (8 * (lane >> 4) + (lane & 7)) * 64 + ((lane >> 3) & 1) * 16;
                    float d[2][4] = {};
#pragma unroll 4
                    for (int ks = 0; ks < 28; ks++) {
                        uint32_t A[8];
                        ldsm4t(wa + ks * 1024, A); ldsm4t(wa + ks * 1024 + 32, A + 4);
                        const float2 v = lds2f(wmbuf + 28672 + ks * 32 + (lane & 3) * 8);
                        mma16816(d[0], A[0], A[1], A[2], A[3], __float_as_uint(v.x), __float_as_uint(v.y));
                        mma16816(d[1], A[4], A[5], A[6], A[7], __float_as_uint(v.x), __float_as_uint(v.y));
                    }
                    const int q = lane & 3, col = mcol + 8 * q + (lane >> 2);
                    const uint32_t word = mod_word(q == 0 ? d[0][0] : q == 1 ? d[0][2] : q == 2 ? d[1][0] : d[1][2], col, target);
#pragma unroll
                    for (int i = 0; i < 8; i++) st_relaxed(g_mod + i * 6 * DM + col, word);
                }
                warp_arrive(BAR(B_WMFREE));
                mbar_wait(BAR(B_VRFULL), 0);
                l2_prefetch_e((const char*)p.wg + (size_t)b * 12544, 12544);
                l2_prefetch_e((const char*)p.wu + (size_t)b * 12544, 12544);
#pragma unroll 1
                for (int k = 0; k < (r < 12 ? 2 : 1); k++) {
                    const int u = 28 * kh + r + 16 * k;
                    expect_e(BAR(B_XFULL + k), 7168);
                    tma3_e(sb + OFF_Y + 102400, &p.dn, 0, 32 * u, 7 * j, BAR(B_XFULL + k));
                    tma3_e(sb + OFF_Y + 102400 + 3584, &p.dn, 0, 32 * u, 7 * (j ^ 1), BAR(B_XFULL + k));
                    mbar_wait(BAR(B_XFULL + k), 1);
                    asm volatile("{\n.reg .pred p;\nelect.sync _|p, 0xffffffff;\n@p cp.async.bulk.global.shared::cta.bulk_group [%0], [%1], 7168;\n"
                                 "cp.async.bulk.commit_group;\ncp.async.bulk.wait_group 0;\n}" ::"l"(g_wd + (size_t)(u * 4 + nq) * 1792), "r"(sb + OFF_Y + 102400) : "memory");
                    __syncwarp();
                }
                warp_arrive(BAR(B_FULLK));
                fence_gpu();
                if (lane < 16) st_relaxed(g_flag + (8 * lane + j) * 128 + 96 + r, target);
            }
        if (warp == 8 || warp == 11) {
            const int sec = warp == 11;
            if (sec) ring_loader<1>(p, sb, r, j, lane); else ring_loader<0>(p, sb, r, j, lane);
            mbar_wait(BAR(B_DONE), 0);
        } else if (warp == 9) {
#pragma unroll
            for (int ev = 0; ev < 4; ev++) { expect_e(BAR(B_GFULL + ev), ev < 2 ? HALF / 2 : 16384 + 4096); expect_e(BAR(B_XFULL + 2 + ev), ev < 2 ? HALF / 2 : HALF - 16384); }
            mbar_wait(BAR(B_PUB + 2), 0);
            const uint32_t* fp = g_flag + b * 128 + 32 + lane;
            const int par = (target - 1) & 1;
#pragma unroll 1
            for (int n = 0, ev = 0; ev < 4; n++) {
                if (ev == 1) mbar_wait(BAR(B_PUB + 3), 0);
                uint32_t ok = __ballot_sync(~0u, (int)(ld_relaxed(fp) - target) >= 0) >> (8 * ev);
                while ((ok & 0xFFu) == 0xFFu) {
                    if (ev == 1) mbar_wait(BAR(B_FULLK), 1);
                    asm volatile("fence.acquire.gpu;" ::: "memory");
                    fence_async_global();
                    const int tile = (ev & 1) + (ev >> 1) * par * 2;
                    const uint32_t dst = sb + (ev == 0 ? OFF_X : OFF_Y + (ev & 1) * HALF), first = ev < 2 ? HALF / 2 : 16384;
                    const char* src = (const char*)(act + RB_O + ((ev >> 1) * 2 + tile) * 14336);
                    if (ev >= 2) bulk_e(sb + OFF_X + X_STAT + (ev & 1) * 49152, act + RB_ST + tile * 1024, 4096, BAR(B_GFULL + ev));
                    bulk_e(dst, src, first, BAR(B_GFULL + ev));
                    bulk_e(dst + first, src + first, HALF - first, BAR(B_XFULL + 2 + ev));
                    if (ev) PROFH(4 + ev);
                    ev++; ok >>= 8;
                }
                if (n > SPIN_LIMIT) __trap();
            }
            mbar_wait(BAR(B_XFULL + 5), 1);
#pragma unroll 1
            for (int hf = 0; hf < 2; hf++) {
                const int tile = (par ^ 1) * 2 + hf;
                uint4* xz = (uint4*)(act + RB_X1 + tile * 14336 + j * 1792) + lane;
#pragma unroll
                for (int i = 0; i < 14; i++) xz[i * 32] = make_uint4(0, 0, 0, 0);
                ((uint4*)(act + RB_ST + (tile * 8 + j) * 128))[lane] = make_uint4(0, 0, 0, 0);
            }
#pragma unroll 1
            for (int ps = 0; ps < 3; ps++) {
                mbar_wait(BAR(B_PUB + 6 + ps), 0);
                wait_flags(g_flag + b * 128 + 64 + lane, target, (0x55u << kh) << (8 * ps));
                warp_arrive(BAR(B_HRDY + ps));
                PROFH(9 + ps);
            }
        } else {
#pragma unroll 1
            for (int k = 0; k < 9; k++) {
                uint32_t* fp = k < 2 ? g_flag + (b + 8 * lane) * 128 + k * 8 + lane : g_flag + (8 * r + lane) * 128 + 16 + k * 8 + j;
                mbar_wait(BAR(B_PUB + k), 0);
                if (k != 4 && k != 5) fence_gpu();
                if (k < 2 ? (lane == 1 || lane == 2) : lane < 8) st_relaxed(fp, target);
                if (k >= 3 && k <= 5) PROFH(k - 3);
            }
        }
    }
}

__global__ void __cluster_dims__(2, 1, 1) __launch_bounds__(384, 1) fused_block_kernel(const __grid_constant__ Params p) {
    extern __shared__ __align__(1024) unsigned char smem[];
    const uint32_t sb = (uint32_t)__cvta_generic_to_shared(smem);
    const int tid = threadIdx.x, lane = tid & 31, warp = __shfl_sync(~0u, tid >> 5, 0);
    const int m = blockIdx.x >> 1;
    int r, nq;
    if (m < 4) { r = 15; nq = m; }
    else if (m < 36) { r = (m - 4) & 7; nq = (m - 4) >> 3; }
    else { nq = (m - 36) / 7; r = m - 28 - 7 * nq; }
    const int j = opaque(2 * nq + (blockIdx.x & 1)), b = 8 * r + j, fs = 4 * kh + nq;
#define act (p.actb + (size_t)r * RB_WORDS)
    constexpr uint32_t sc = 0;
    if (lane == 0 && warp < 9 && warp != 6 && warp != 7) {
        const int i0 = warp == 8 ? 0 : 8 + 8 * warp, cnt = warp == 0 || warp == 8 ? 1 : warp < 3 ? 2 : 8;
#pragma unroll
        for (int k = 0; k < 8; k++) if (i0 + k != B_WMFULL) mbar_init(BAR(i0 + k), cnt);
        if (warp == 8) mbar_init(BAR(B_WMFULL), 1);
        asm volatile("fence.mbarrier_init.release.cluster;" ::: "memory");
        fence_async_smem();
    }

    if (warp >= 8) {
        const int lane = fresh_tid() & 31;
        const bool early = kh == 0, gemv = r < 14;
        const int mcol = early ? 16 * (4 * r + nq) : 2 * DM + 32 * (4 * r + nq);
        const uint32_t wmbuf = sb + OFF_Y + HALF;
        if (warp == 8) {
            __syncwarp();
            expect_e(BAR(B_WMFULL), gemv ? 28672 >> early : 0);
            if (early && gemv) { tma3_e(wmbuf, &p.wm, mcol, 0, 0, BAR(B_WMFULL)); tma3_e(wmbuf + 7168, &p.wm, mcol, 224, 0, BAR(B_WMFULL)); }
#pragma unroll
            for (int kb = 0; kb < XFIRST; kb++) {
                expect_e(BAR(B_XFULL + kb), 16384);
                tma3_e(sb + OFF_X + kb * 16384, &p.xm, 64 * kb, 128 * r, 0, BAR(B_XFULL + kb));
            }
        }
        asm volatile("setmaxnreg.dec.sync.aligned.u32 56;");
        if (warp == 9) {
#pragma unroll
            for (int i = 56; i < 64; i++) init_e(BAR(i), 1);
            fence_async_smem();
        }
        bar_arrive(0, 384);
        asm volatile("barrier.cluster.arrive.relaxed.aligned;" ::: "memory");
        if (warp == 8) {
#pragma unroll
            for (int kb = XFIRST; kb < 7; kb++) {
                expect_e(BAR(B_XFULL + kb), 16384);
                tma3_e(sb + OFF_X + kb * 16384, &p.xm, 64 * kb, 128 * r, 0, BAR(B_XFULL + kb));
            }
            if (KDELAY >= 0) { mbar_wait(BAR(B_XFULL + KDELAY), 0); l2_prefetch_e((const char*)p.wqkv + (size_t)b * 9408, 9408); }
#pragma unroll 1
            for (int mt = 0; mt < 4; mt++) {
                if (mt == 1) bar_sync(9, 384);
                if (mt == 3) mbar_wait(BAR(B_WMFREE), 0);
                if (mt) mbar_wait(BAR(mt == 1 ? B_MOD1 : mt == 2 ? B_XFREE : B_VRFULL), 0);
                const uint32_t bar = BAR(mt == 3 ? B_WOFULL : B_FULLK + mt), dst = sb + (mt < 2 ? OFF_Y : OFF_X) + (mt & 1) * HALF;
                const int c0 = (mt < 2 ? DM + DM * mt : 0) + 56 * j - 8 * kh;
                if (!sc) {
                    expect_e(bar, HALF);
                    tma3_e(dst, mt == 3 ? &p.wo : &p.qkv, c0, 0, 0, bar);
                    tma3_e(dst + HALF / 2, mt == 3 ? &p.wo : &p.qkv, c0, 224, 0, bar);
                }
            }
        } else {
            if (KDELAY < 0 && warp == 10) l2_prefetch_e((const char*)p.wqkv + (size_t)b * 9408, 9408);
            bar_sync(9, 384);
            if (sc) return;
            if (warp == 11 && early) {
                const uint32_t target = lds1(sb + M_EPOCH) + 1;
                mbar_wait(BAR(B_GEMV), 0);
                float sum = 0.f;
#pragma unroll
                for (int i = 0; i < 8; i++) sum += *(const float*)(smem + OFF_Y + HALF + 29696 + (i * 16 + (lane & 15)) * 4);
                uint32_t* mg = g_mod + mcol + (lane & 15) + (lane >> 4) * 4 * 6 * DM;
                const uint32_t word = mod_word(sum, mcol, target);
                if (gemv) { st_relaxed(mg, word); st_relaxed(mg + 6 * DM, word); st_relaxed(mg + 12 * DM, word); st_relaxed(mg + 18 * DM, word); }
            }
        }
    }
    if (LIKELY(warp < 8)) {
        const int w = warp >> 2, wi = warp & 3;
#define COORDS const int t = fresh_tid() & 127, lane = t & 31, q = lane & 3, lr = lane >> 2, ra = 64 * w + 16 * wi + lr; \
        const uint32_t lx = (lane >> 4) ^ (lane & 7), mrow = (64 * w + 16 * wi + ((lane >> 3) & 1) * 8 + (lane & 7)) * 128; \
        (void)q; (void)lr; (void)ra; (void)lx; (void)mrow;
        const int sid = 2 * (j & 3) + w;
#define RUN(k) (!sc || sid == (k))
#define WAIT(i, par) mbar_wait_c(BAR(i), (par) | sc)
        constexpr uint64_t DB128 = dconst(4096, 1024, 1);
        {
            const int wd = fresh_tid();
            const uint32_t cb = wd < 224 ? __ldg((const uint32_t*)p.c + wd) : 0u;
            if (wd == 255 && !sc) sts1(sb + M_EPOCH, atomicAdd(&g_ticket, 1u) / NCTA);
            sts1(sb + OFF_Y + HALF + 28672 + (wd >> 3) * 32 + (wd & 3) * 8 + (wd & 4), pack2(silu_bf(cb & 0xFFFFu), silu_bf(cb >> 16)));
        }
        bar_arrive(9, 384);
        bar_sync(0, 384);
        asm volatile("barrier.cluster.arrive.relaxed.aligned;" ::: "memory");
        asm volatile("setmaxnreg.inc.sync.aligned.u32 224;");
        PROFC(0);
        uint32_t xr[16];
        {
            COORDS
            uint32_t h[112];
            uint32_t ra2, na2, rb2, nb2;
            const int mi = min(128 * w + t, 223);
            const uint4* msrc = mod_src(mi, r, j, false);
            uint4 mv;
            {
                float ds[4] = {}, da[2][4] = {}, db[2][4] = {};
                const uint32_t ONE2 = 0x3F803F80u;
#pragma unroll
                for (int kb = 0; kb < 7; kb++) {
                    if (kb == GEMV_AT && kh == 0) { WAIT(B_WMFULL, 0); gemv_part(sb + OFF_Y + HALF, warp, lane); warp_arrive(BAR(B_GEMV)); }
                    WAIT(B_XFULL + kb, 0);
#pragma unroll
                    for (int k4 = 0; k4 < 4; k4++) ldsm4(sb + OFF_X + mrow + kb * 16384 + (((2 * k4) ^ lx) << 4), h + 16 * kb + 4 * k4);
#pragma unroll
                    for (int k4 = 0; k4 < 4; k4++) {
                        const uint32_t* f = h + 16 * kb + 4 * k4;
                        mma16816(ds, f[0], f[1], f[2], f[3], ONE2, ONE2);
                        mma1688(da[0], f[0], f[1], f[0]); mma1688(db[0], f[0], f[1], f[1]);
                        mma1688(da[1], f[2], f[3], f[2]); mma1688(db[1], f[2], f[3], f[3]);
                    }
                }
#pragma unroll
                for (int i = 0; i < 4; i++) {
                    const int ch = 7 * j + 2 * i + (lane >> 4);
                    ldsm4(sb + OFF_X + mrow + (ch >> 3) * 16384 + (((ch ^ lane) & 7) << 4), xr + 4 * i);
                }
                mv = ld_relaxed4(msrc);
                warp_arrive(BAR(B_XFREE));
                float qa = (lr & 1) ? da[0][1] + da[1][1] : da[0][0] + da[1][0];
                float qb = (lr & 1) ? db[0][3] + db[1][3] : db[0][2] + db[1][2];
                const int src = (lane & ~3) | (lr >> 1);
                qa = __shfl_sync(~0u, qa, src);
                qb = __shfl_sync(~0u, qb, src);
                ln_coeffs(ds[0] * (1.f / DM), qa * (1.f / DM), ra2, na2);
                ln_coeffs(ds[2] * (1.f / DM), qb * (1.f / DM), rb2, nb2);
#pragma unroll
                for (int i = 0; i < 4 * NPRE; i += 2) { h[i] = hfma2(h[i], ra2, na2); h[i + 1] = hfma2(h[i + 1], rb2, nb2); }
            }
            PROFC(1);
            {
                float ak[28], av[28], aq[28];
                uint32_t kp[14], vp[14];
                const uint64_t bq0 = (DB128 & ~0xFFFFFFFFull) | (mkdesc(sb + OFF_X, DB128) + kh), bk0 = bq0 + (OFF_Y >> 4), bv0 = bk0 + (HALF >> 4);
                uint32_t* kvg = act + RB_KV + j * 7168 + (8 * w + 2 * wi) * 224 + lane;
                mod_store(sb, mv, msrc, mi);
                bar_sync(3, 256);
                if (warp == 0) warp_arrive(BAR(B_MOD1));
                WAIT(B_FULLK, 0);
                PROFC(2);
                reg_def<28>(ak);
#pragma unroll
                for (int g4 = 0; g4 < 4; g4++) {
#pragma unroll
                    for (int ks = 7 * g4; ks < 7 * g4 + 7; ks++) {
                        const uint4 st = *(const uint4*)(smem + M_ST + ks * 64 + q * 16);
                        if (ks >= NPRE) {
                            h[4 * ks] = hfma2(h[4 * ks], ra2, na2); h[4 * ks + 1] = hfma2(h[4 * ks + 1], rb2, nb2);
                            h[4 * ks + 2] = hfma2(h[4 * ks + 2], ra2, na2); h[4 * ks + 3] = hfma2(h[4 * ks + 3], rb2, nb2);
                        }
                        h[4 * ks] = hfma2(h[4 * ks], st.x, st.y); h[4 * ks + 1] = hfma2(h[4 * ks + 1], st.x, st.y);
                        h[4 * ks + 2] = hfma2(h[4 * ks + 2], st.z, st.w); h[4 * ks + 3] = hfma2(h[4 * ks + 3], st.z, st.w);
                    }
                    WG_FENCE();
#pragma unroll
                    for (int ks = 7 * g4; ks < 7 * g4 + 7; ks++) wgmma_rl_56(ak, h[4 * ks], h[4 * ks + 1], h[4 * ks + 2], h[4 * ks + 3], bk0 + ks * 128, ks != 0);
                }
                WG_COMMIT();
                PROFC(3);
                reg_def<28>(av);
                WAIT(B_FULLV, 0);
                WG_FENCE();
#pragma unroll
                for (int ks = 0; ks < 8; ks++) wgmma_rl_56(av, h[4 * ks], h[4 * ks + 1], h[4 * ks + 2], h[4 * ks + 3], bv0 + ks * 128, ks != 0);
                WG_COMMIT();
                WG_WAIT(1);
                reg_fence<28>(ak);
#pragma unroll
                for (int g = 0; g < 7; g++) {
                    kp[2 * g] = pack2(ak[4 * g], ak[4 * g + 1]); kp[2 * g + 1] = pack2(ak[4 * g + 2], ak[4 * g + 3]);
                    kvg[g * 32] = kp[2 * g]; kvg[224 + g * 32] = kp[2 * g + 1];
                }
                warp_arrive(BAR(B_PUB));
                PROFC(4);
                if (KEARLY) WAIT(B_FULLV, 0);
                WG_FENCE();
#pragma unroll
                for (int ks = KEARLY ? 0 : 8; ks < 28; ks++) wgmma_rl_56(av, h[4 * ks], h[4 * ks + 1], h[4 * ks + 2], h[4 * ks + 3], bv0 + ks * 128, ks != 0);
                WG_COMMIT();
                WAIT(B_FULLQ, 0);
                reg_def<28>(aq);
                WG_FENCE();
#pragma unroll
                for (int ks = 0; ks < 8; ks++) wgmma_rl_56(aq, h[4 * ks], h[4 * ks + 1], h[4 * ks + 2], h[4 * ks + 3], bq0 + ks * 128, ks != 0);
                WG_COMMIT();
                WG_WAIT(1);
                reg_fence<28>(av);
#pragma unroll
                for (int g = 0; g < 7; g++) {
                    vp[2 * g] = pack2(av[4 * g], av[4 * g + 1]); vp[2 * g + 1] = pack2(av[4 * g + 2], av[4 * g + 3]);
                    kvg[3584 + g * 32] = vp[2 * g]; kvg[3584 + 224 + g * 32] = vp[2 * g + 1];
                }
                warp_arrive(BAR(B_PUB + 1));
                PROFC(5);
                WG_FENCE();
#pragma unroll
                for (int ks = 8; ks < 28; ks++) wgmma_rl_56(aq, h[4 * ks], h[4 * ks + 1], h[4 * ks + 2], h[4 * ks + 3], bq0 + ks * 128, 1);
                WG_COMMIT();
                WAIT(B_PUB + 1, 0);
                const uint32_t rg = 8 * w + 2 * wi + ((lane >> 3) & 1);
                const uint32_t ko = sb + OFF_Y + Y_KOWN + rg * 896 + (lane & 7) * 16, qo = sb + OFF_Y + Y_Q + rg * 1024 + (lane >> 4) * 128 + (lane & 7) * 16;
#pragma unroll
                for (int g = 0; g < 6; g += 2) {
                    stsm4(ko + (g + (lane >> 4)) * 128, kp[2 * g], kp[2 * g + 1], kp[2 * g + 2], kp[2 * g + 3]);
                    stsm4(ko + (Y_VOWN - Y_KOWN) + (g + (lane >> 4)) * 128, vp[2 * g], vp[2 * g + 1], vp[2 * g + 2], vp[2 * g + 3]);
                }
                stsm4(ko + (lane >> 4) * (Y_VOWN - Y_KOWN) + 6 * 128, kp[12], kp[13], vp[12], vp[13]);
                WG_WAIT(0);
                reg_fence<28>(aq);
                __syncwarp();
                if (lane < 3 && w == 1) mbar_arrive(BAR(B_EMPTY + lane));
                uint32_t qp[14];
#pragma unroll
                for (int i = 0; i < 14; i++) qp[i] = pack2(aq[2 * i], aq[2 * i + 1]);
                stsm4(qo, qp[0], qp[1], qp[2], qp[3]);
                stsm4(qo + 256, qp[4], qp[5], q < 2 ? qp[6] : 0u, q < 2 ? qp[7] : 0u);
                stsm4(qo + 512, q < 2 ? 0u : qp[6], q < 2 ? 0u : qp[7], qp[8], qp[9]);
                stsm4(qo + 768, qp[10], qp[11], qp[12], qp[13]);
                if (!sc) bar_sync(3, 256);
            }
        }
        PROFC(6);
        WAIT(B_KRFULL, 0);
        if (ATT_OFF && w == ATT_WG) { const uint32_t t0 = clock(); while (clock() - t0 < ATT_OFF) {} }
        PROFC(7);
        if (RUN(2)) {
#pragma unroll 1
            for (int hf = sc; hf < 2; hf++) {
                COORDS
                float s[136];
                float na = 0.f, nb = 0.f;
                const float CS = 0.18898223650461361f * 1.4426950408889634f;
                const int kg0 = 8 * hf + 2 * wi;
                const int pmin = 16 - 8 * r - 4 * hf - wi;
                const float NEG = __int_as_float(0xFF800000);
                {
                    uint32_t F[8];
                    const uint32_t qa = sb + OFF_Y + Y_Q + (kg0 + ((lane >> 3) & 1)) * 1024 + (4 * w + (lane >> 4)) * 128 + (lane & 7) * 16;
                    ldsm4(qa, F); ldsm4(qa + 256, F + 4);
                    uint32_t ka = sb + OFF_Y + Y_K + kg0 * 896 + (3 * w + (lane >> 3)) * 128 + (lane & 7) * 16;
#pragma unroll
                    for (int g = 0; g < 34; g++) {
                        uint32_t B[4];
                        if (g >= 12 && g % 4 == 0) ka += __float_as_uint(s[4 * (g - 12)]) & p.zero;
                        ldsm4(ka + g * 896, B);
                        mma16816_first(s + 4 * g, F[0], F[1], F[2], F[3], B[0], B[1]);
                        mma16816_v(s + 4 * g, F[4], F[5], F[6], F[7], B[2], B[3]);
                    }
                    const bool c0 = 2 * q > lr, c1 = 2 * q + 1 > lr;
                    if (!c0) { s[0] = NEG; s[6] = NEG; }
                    if (!c1) { s[1] = NEG; s[7] = NEG; }
                    s[2] = NEG; s[3] = NEG;
                    if (c0) { s[128] = NEG; s[134] = NEG; }
                    if (c1) { s[129] = NEG; s[135] = NEG; }
                    s[132] = NEG; s[133] = NEG;
                    float ma = NEG, mb = NEG;
#pragma unroll
                    for (int pp = 0; pp < 17; pp++) {
                        const float* e = s + 8 * pp;
                        const float bias = pp < pmin ? NEG : 0.f;
                        ma = fmaxf(ma, fmaxf(fmaxf(e[0], e[1]), fmaxf(e[4], e[5])) + bias);
                        mb = fmaxf(mb, fmaxf(fmaxf(e[2], e[3]), fmaxf(e[6], e[7])) + bias);
                    }
                    ma = fmaxf(ma, __shfl_xor_sync(~0u, ma, 1)); mb = fmaxf(mb, __shfl_xor_sync(~0u, mb, 1));
                    ma = fmaxf(ma, __shfl_xor_sync(~0u, ma, 2)); mb = fmaxf(mb, __shfl_xor_sync(~0u, mb, 2));
                    na = -ma * CS; nb = -mb * CS;
                }
                PROFC(8 + 3 * hf);
                {
                    WAIT(B_VRFULL, 0);
                    float o[16] = {}, rs[4] = {};
                    uint32_t pk[2];
                    const uint32_t va = sb + OFF_Y + Y_VR + (kg0 + ((lane >> 3) & 1)) * 896 + (3 * w + (lane >> 4)) * 128 + (lane & 7) * 16;
#pragma unroll
                    for (int pp = 0; pp < 17; pp++) {
                        uint32_t B[8];
                        const uint32_t v = va + pp * 1792 + (pp == 16 || (pp >= 9 && kg0 + 2 * pp >= 32) ? Y_VOWN - 32 * 896 : 0);
                        ldsm4t(v, B); ldsm4t(v + 256, B + 4);
                        float e[8];
                        const float bias = __uint_as_float((pp < pmin ? 0xFF800000u : 0u) | ((pp < 2 ? B[0] : pk[pp & 1]) & p.zero));
#pragma unroll
                        for (int i = 0; i < 8; i++) e[i] = ex2(fmaf(s[8 * pp + i], CS, ((i & 2) ? nb : na) + bias));
                        const uint32_t p0 = pack2(e[0], e[1]), p1 = pack2(e[2], e[3]), p2 = pack2(e[4], e[5]), p3 = pack2(e[6], e[7]);
                        pk[pp & 1] = p3;
                        mma16816(rs, p0, p1, p2, p3, 0x3F803F80u, 0x3F803F80u);
#pragma unroll
                        for (int g = 0; g < 4; g++) mma16816(o + 4 * g, p0, p1, p2, p3, B[2 * g], B[2 * g + 1]);
                    }
                    PROFC(9 + 3 * hf);
                    const float ia = rcp(rs[0]), ib = rcp(rs[2]);
                    uint32_t* og = act + RB_O + hf * 14336 + (7 * j + 3 * w) * 256 + wi * 64 + lane;
#pragma unroll
                    for (int g = 0; g < 4; g++) {
                        if ((g == 3 - 3 * w) ? ((q >> 1) == w) : true) {
                            og[g * 256] = pack2(o[4 * g] * ia, o[4 * g + 1] * ia);
                            og[g * 256 + 32] = pack2(o[4 * g + 2] * ib, o[4 * g + 3] * ib);
                        }
                    }
                    warp_arrive(BAR(B_PUB + 2 + hf));
                    PROFC(10 + 3 * hf);
                }
            }
        }
        uint32_t x1p[14];
        COORDS
        constexpr uint64_t DT = dconst(1024, 128, 0);
        const int tile = opaque((lds1(sb + M_EPOCH) & 1) * 2 + w);
        if (RUN(4)) {
            float ac[28];
            const uint32_t ad = mkdesc(sb + (w ? OFF_Y + HALF : OFF_X), DT), bd = mkdesc(sb + OFF_X + HALF, DB128) + kh;
            WAIT(B_WOFULL, 0);
            WAIT(B_MOD1, 1);
            WAIT(B_GFULL + w, 0);
            PROFC(28);
            reg_def<28>(ac);
#pragma unroll 1
            for (int u = 0; u < 4; u++) {
                if (u == 2) WAIT(B_XFULL + 2 + w, 1);
                WG_FENCE();
#pragma unroll
                for (int i = 0; i < 7; i++) wgmma_ss_56<DT, DB128>(ac, ad + (7 * u + i) * 128, bd + (7 * u + i) * 128, (u | i) != 0);
            }
            WG_COMMIT();
            WG_WAIT(0);
            reg_fence<28>(ac);
            PROFC(14);
            __syncwarp();
            if (lane < 3) mbar_arrive(BAR(B_EMPTY + 4 - w + lane));
            if (lane < 3 && w == 0) mbar_arrive(BAR(B_EMPTY + lane));
            float ds[4] = {}, da[4] = {}, db[4] = {};
            uint32_t* xo = act + RB_X1 + tile * 14336 + 7 * j * 256 + wi * 64 + lane;
#pragma unroll
            for (int g = 0; g < 7; g++) {
                const float2 ga = *(const float2*)(smem + M_G + (8 * g + 2 * q) * 4);
                x1p[2 * g] = pack2(fmaf(ga.x, ac[4 * g], bf_lo(xr[2 * g])), fmaf(ga.y, ac[4 * g + 1], bf_hi(xr[2 * g])));
                x1p[2 * g + 1] = pack2(fmaf(ga.x, ac[4 * g + 2], bf_lo(xr[2 * g + 1])), fmaf(ga.y, ac[4 * g + 3], bf_hi(xr[2 * g + 1])));
                st_relaxed(xo + g * 256, nz(x1p[2 * g])); st_relaxed(xo + g * 256 + 32, nz(x1p[2 * g + 1]));
                mma1688(ds, x1p[2 * g], x1p[2 * g + 1], 0x3F803F80u);
                mma1688(da, x1p[2 * g], x1p[2 * g + 1], x1p[2 * g]);
                mma1688(db, x1p[2 * g], x1p[2 * g + 1], x1p[2 * g + 1]);
            }
            const int src = (lane & ~3) | (lr >> 1);
            const float qa = __shfl_sync(~0u, (lr & 1) ? da[1] : da[0], src), qb = __shfl_sync(~0u, (lr & 1) ? db[3] : db[2], src);
            const float kk = (q & 1) ? ((q & 2) ? qb : qa) : ((q & 2) ? ds[2] : ds[0]);
            st_relaxed(act + RB_ST + ((tile * 8 + j) * 64 + 16 * wi + lr + 4 * (q & 2)) * 2 + (q & 1), nz(__float_as_uint(kk)));
            __syncwarp();
            if (lane < 2) mbar_arrive(BAR(B_PUB + 4 + w));
        } else reg_def<14>(x1p);
        PROFC(15);
        uint32_t h2a[32], h2b[24];
        {
            const int fa = pass_f(fs, 0), fb = pass_f(fs, 1), fc = pass_f(fs, 2);
            uint32_t* h2g = act + RB_H2 + (8 * w + 2 * wi) * 32 + lane;
            const uint32_t a0 = mkdesc(sb + OFF_Y + w * HALF, DT);
            if (RUN(3)) {
                uint32_t ra2, na2, rb2, nb2;
                {
                    const uint32_t* sg = act + RB_ST + ((tile * 8 + 2 * q) * 64 + 16 * wi + lr) * 2;
                    uint2 u[4];
                    WAIT(B_GFULL + 2 + w, 0);
                    PROFC(16);
#pragma unroll
                    for (int i = 0; i < 4; i++) { const float2 v = lds2f(sb + OFF_X + X_STAT + w * 49152 + ((2 * q + (i >> 1)) * 64 + 16 * wi + lr + 8 * (i & 1)) * 8); u[i] = make_uint2(__float_as_uint(v.x), __float_as_uint(v.y)); }
                    while (__any_sync(~0u, min(min(min(u[0].x, u[0].y), min(u[1].x, u[1].y)), min(min(u[2].x, u[2].y), min(u[3].x, u[3].y))) < 1u - sc)) {
#pragma unroll
                        for (int i = 0; i < 4; i++) u[i] = ld_relaxed2(sg + (i >> 1) * 128 + (i & 1) * 16);
                    }
                    warp_arrive(BAR(B_EMPTY + 3 + 3 * w));
                    float v[4] = {__uint_as_float(u[0].x) + __uint_as_float(u[2].x), __uint_as_float(u[0].y) + __uint_as_float(u[2].y),
                                  __uint_as_float(u[1].x) + __uint_as_float(u[3].x), __uint_as_float(u[1].y) + __uint_as_float(u[3].y)};
#pragma unroll
                    for (int i = 0; i < 4; i++) { v[i] += __shfl_xor_sync(~0u, v[i], 1); v[i] += __shfl_xor_sync(~0u, v[i], 2); }
                    ln_coeffs(v[0] * (1.f / DM), v[1] * (1.f / DM), ra2, na2);
                    ln_coeffs(v[2] * (1.f / DM), v[3] * (1.f / DM), rb2, nb2);
                }
                const uint32_t ha = sb + OFF_Y + w * HALF + (lane >> 4) * 1024 + (2 * wi + ((lane >> 3) & 1)) * 128 + (lane & 7) * 16;
                const uint32_t sta = sb + M_ST + q * 16;
                const uint32_t* xg = act + RB_X1 + tile * 14336 + (lane >> 4) * 256 + wi * 64 + (lane & 15) * 4;
                uint32_t x[8];
                const uint32_t xs = sb + OFF_Y + w * HALF + (lane >> 4) * 1024 + wi * 256 + (lane & 15) * 16;
                uint4 st[2];
                auto load = [&](int s) {
                    if (s == 4) mbar_wait_c(BAR(B_XFULL + 4 + w), 1);
                    ldsm4(ha + s * 4096, x); ldsm4(ha + s * 4096 + 2048, x + 4);
                    st[0] = lds4(sta + s * 128); st[1] = lds4(sta + s * 128 + 64);
                };
                auto prep = [&](int s, uint32_t* f) {
                    if (__any_sync(~0u, min(min(min(x[0], x[1]), min(x[2], x[3])), min(min(x[4], x[5]), min(x[6], x[7]))) < 1u - sc)) {
                        WG_WAIT(0);
                        x1_fix(xg, xs, s);
                        ldsm4(ha + s * 4096, x); ldsm4(ha + s * 4096 + 2048, x + 4);
                    }
#pragma unroll
                    for (int i = 0; i < 2; i++) {
                        f[4 * i] = hfma2(hfma2(x[4 * i], ra2, na2), st[i].x, st[i].y); f[4 * i + 1] = hfma2(hfma2(x[4 * i + 1], rb2, nb2), st[i].x, st[i].y);
                        f[4 * i + 2] = hfma2(hfma2(x[4 * i + 2], ra2, na2), st[i].z, st[i].w); f[4 * i + 3] = hfma2(hfma2(x[4 * i + 3], rb2, nb2), st[i].z, st[i].w);
                    }
                    if (s < 13) load(s + 1);
                    stsm4(ha + s * 4096, f[0], f[1], f[2], f[3]); stsm4(ha + s * 4096 + 2048, f[4], f[5], f[6], f[7]);
                };
                float ac[128];
                uint32_t fr[3][8];
                uint64_t bd = (DB128 & ~0xFFFFFFFFull) | mkdesc(sb, DB128);
                reg_def<128>(ac);
                load(0);
                prep(0, fr[0]);
                PROFC(17);
#pragma unroll
                for (int s = 0; s < 14; s++) {
                    const uint32_t* f = fr[s % 3];
                    WAIT(B_FULL + g1_slot(s), s >= 7);
                    WG_FENCE();
                    wgmma_rl_256(ac, f[0], f[1], f[2], f[3], bd, s != 0);
                    wgmma_rl_256(ac, f[4], f[5], f[6], f[7], bd + 128, 1);
                    bd += s == 6 ? p.zero - 6 * 1024ull : 1024;
                    WG_COMMIT();
                    if (s < 13) prep(s + 1, fr[(s + 1) % 3]);
                    if (s > 0) { WG_WAIT(1); warp_arrive(BAR(B_EMPTY + g1_slot(s - 1))); }
                }
                fence_async_smem();
                PROFC(18);
                WG_WAIT(0);
                reg_fence<128>(ac);
                warp_arrive(BAR(B_EMPTY + 6));
#pragma unroll
                for (int g = 0; g < 16; g++) {
                    h2a[2 * g] = hmul2(pack2_relu(ac[4 * g], ac[4 * g + 1]), pack2(ac[64 + 4 * g], ac[64 + 4 * g + 1]));
                    h2a[2 * g + 1] = hmul2(pack2_relu(ac[4 * g + 2], ac[4 * g + 3]), pack2(ac[64 + 4 * g + 2], ac[64 + 4 * g + 3]));
                }
                bar_sync(1 + w, 128);
            } else reg_def<32>(h2a);
            PROFC(19);
            if (RUN(5)) {
                float ac[64];
                reg_def<64>(ac);
                const uint32_t bx = mkdesc(sb, dconst(8192, 1024, 1));
#pragma unroll kB
                for (int s = 0; s < 7; s++) {
                    WAIT(B_FULL + s, 0);
                    const uint32_t ad = a0 + s * 512, bd = bx + (slot_off(s) >> 4);
                    WG_FENCE();
#pragma unroll
                    for (int k = 0; k < 4; k++) wgmma_ss_128<DT, DB128>(ac, ad + k * 128, bd + k * 128, (s | k) != 0);
                    WG_COMMIT();
                    if (s == 1) {
#pragma unroll
                        for (int g = 0; g < 16; g++) { h2g[(fa / 8 + g) * 512] = h2a[2 * g]; h2g[(fa / 8 + g) * 512 + 32] = h2a[2 * g + 1]; }
                        warp_arrive(BAR(B_PUB + 6));
                    }
                    if (s > 0) { WG_WAIT(1); warp_arrive(BAR(B_EMPTY + s - 1)); }
                }
                WG_WAIT(0);
                reg_fence<64>(ac);
                warp_arrive(BAR(B_EMPTY + 6));
#pragma unroll
                for (int g = 0; g < 8; g++) {
                    h2b[2 * g] = hmul2(pack2_relu(ac[4 * g], ac[4 * g + 1]), pack2(ac[32 + 4 * g], ac[32 + 4 * g + 1]));
                    h2b[2 * g + 1] = hmul2(pack2_relu(ac[4 * g + 2], ac[4 * g + 3]), pack2(ac[32 + 4 * g + 2], ac[32 + 4 * g + 3]));
                }
            } else reg_def<16>(h2b);
            PROFC(27);
            if (RUN(6)) {
                float ac[32];
                reg_def<32>(ac);
                const uint32_t bx = mkdesc(sb, dconst(4096, 512, 2));
#pragma unroll kC
                for (int s = 0; s < 7; s++) {
                    WAIT(B_FULL + s, 1);
                    const uint32_t ad = a0 + s * 512, bd = bx + (slot_off(s) >> 4);
                    WG_FENCE();
#pragma unroll
                    for (int k = 0; k < 4; k++) wgmma_ss_64<DT, dconst(4096, 512, 2)>(ac, ad + k * 128, bd + k * 64, (s | k) != 0);
                    WG_COMMIT();
                    if (s == 1) {
#pragma unroll
                        for (int g = 0; g < 8; g++) { h2g[(fb / 8 + g) * 512] = h2b[2 * g]; h2g[(fb / 8 + g) * 512 + 32] = h2b[2 * g + 1]; }
                        warp_arrive(BAR(B_PUB + 7));
                    }
                    if (s > 0) { WG_WAIT(1); warp_arrive(BAR(B_EMPTY + s - 1)); }
                }
                WG_WAIT(0);
                reg_fence<32>(ac);
                __syncwarp();
                if (lane < 6) mbar_arrive(BAR(B_EMPTY + 6 + lane));
                PROFC(20);
#pragma unroll
                for (int g = 0; g < 4; g++) {
                    h2b[16 + 2 * g] = hmul2(pack2_relu(ac[4 * g], ac[4 * g + 1]), pack2(ac[16 + 4 * g], ac[16 + 4 * g + 1]));
                    h2b[16 + 2 * g + 1] = hmul2(pack2_relu(ac[4 * g + 2], ac[4 * g + 3]), pack2(ac[16 + 4 * g + 2], ac[16 + 4 * g + 3]));
                    h2g[(fc / 8 + g) * 512] = h2b[16 + 2 * g]; h2g[(fc / 8 + g) * 512 + 32] = h2b[16 + 2 * g + 1];
                }
                warp_arrive(BAR(B_PUB + 8));
                asm volatile("barrier.cluster.wait.aligned;" ::: "memory");
                if (lane == 0 && !sc) {
                    uint32_t rb;
                    asm volatile("mapa.shared::cluster.u32 %0, %1, %2;" : "=r"(rb) : "r"(BAR(B_PEER)), "r"(kh ^ 1));
                    asm volatile("mbarrier.arrive.relaxed.cluster.shared::cluster.b64 _, [%0];" ::"r"(rb) : "memory");
                }
            } else reg_def<8>(h2b + 16);
        }
        PROFC(21);
        if (RUN(7)) {
            float ac[56];
            reg_def<56>(ac);
            constexpr uint64_t DAN = dconst(2048, 128, 0);
            constexpr uint64_t DW = dconst(128, 512, 0);
            const uint32_t bx = mkdesc(sb, DW);
#pragma unroll
            for (int e = 0; e < 4; e++) {
                WAIT(B_FULL + e, 0);
                const uint64_t bd = ((DW & ~0xFFFFFFFFull) | bx) + (slot_off(e) >> 4);
                const uint32_t* hh = e < 2 ? h2a + 16 * e : h2b + 16 * (e - 2);
                WG_FENCE();
#pragma unroll
                for (int k = 0; k < (e < 3 ? 4 : 2); k++) wgmma_rl_112(ac, hh[4 * k], hh[4 * k + 1], hh[4 * k + 2], hh[4 * k + 3], bd + (k >> 1) * 512 + (k & 1) * 16, (e | k) != 0);
                WG_COMMIT();
                if (e > 0) { WG_WAIT(1); warp_arrive(BAR(B_EMPTY + e - 1)); }
            }
            PROFC(22);
            uint32_t ad = mkdesc(sb + 4 * 16384 + 8192 + w * 1024, DAN), bd = bx + 4 * 1024, fb_ = BAR(B_FULL + 4), eb_ = BAR(B_EMPTY + 3), par = sc;
#pragma unroll 1
            for (int e = 4; e < 25; e++) {
                mbar_wait_c(fb_, par);
                WG_FENCE();
                wgmma_ss_112<DAN, DW>(ac, ad, bd, 1);
                wgmma_ss_112<DAN, DW>(ac, ad + 256, bd + 16, 1);
                WG_COMMIT();
                WG_WAIT(1);
                warp_arrive(eb_);
                eb_ = fb_ + 8 * (B_EMPTY - B_FULL);
                ad += 1024; bd += 1024; fb_ += 8;
                if (e == 11 || e == 23) { ad -= 12 * 1024; bd -= 12 * 1024; fb_ -= 96; par = (par ^ 1) | sc; }
            }
            mbar_wait_cluster(BAR(B_PEER), sc);
            WG_WAIT(0);
            reg_fence<56>(ac);
            PROFC(24);
            uint32_t rdst, rbar;
            asm volatile("mapa.shared::cluster.u32 %0, %1, %2;" : "=r"(rdst) : "r"(sb + OFF_Y + (5 + w) * 16384 + t * 16), "r"(kh ^ 1 ^ sc));
            asm volatile("mapa.shared::cluster.u32 %0, %1, %2;" : "=r"(rbar) : "r"(BAR(B_XCH + w)), "r"(kh ^ 1 ^ sc));
#pragma unroll
            for (int g = 0; g < 7; g++) {
                const float v0 = ac[28 + 4 * g + 0], v1 = ac[28 + 4 * g + 1];
                const float v2 = ac[28 + 4 * g + 2], v3 = ac[28 + 4 * g + 3];
                if (!sc) asm volatile("st.async.shared::cluster.mbarrier::complete_tx::bytes.v4.f32 [%0], {%1,%2,%3,%4}, [%5];"
                             ::"r"(rdst + g * 2048), "f"(v0), "f"(v1), "f"(v2), "f"(v3), "r"(rbar) : "memory");
            }
            mbar_wait_cluster(BAR(B_XCH + w), sc);
            PROFC(25);
            uint32_t op[16];
#pragma unroll
            for (int g = 0; g < 7; g++) {
                const uint4 rv = *(const uint4*)(smem + OFF_Y + (5 + w) * 16384 + t * 16 + g * 2048);
                const float2 gb = *(const float2*)(smem + M_G + 224 + (8 * g + 2 * q) * 4);
                const float v0 = ac[4 * g + 0] + __uint_as_float(rv.x), v1 = ac[4 * g + 1] + __uint_as_float(rv.y);
                const float v2 = ac[4 * g + 2] + __uint_as_float(rv.z), v3 = ac[4 * g + 3] + __uint_as_float(rv.w);
                op[2 * g] = pack2(fmaf(gb.x, v0, bf_lo(x1p[2 * g])), fmaf(gb.y, v1, bf_hi(x1p[2 * g])));
                op[2 * g + 1] = pack2(fmaf(gb.x, v2, bf_lo(x1p[2 * g + 1])), fmaf(gb.y, v3, bf_hi(x1p[2 * g + 1])));
            }
            WAIT(B_EMPTY + 1, 0);
            const uint32_t oc = sb + OUT_STAGE + warp * 1792;
            const uint32_t oa = oc + (((lane >> 3) & 1) * 8 + (lane & 7)) * 112 + (lane >> 4) * 16;
            stsm4(oa, op[0], op[1], op[2], op[3]); stsm4(oa + 32, op[4], op[5], op[6], op[7]); stsm4(oa + 64, op[8], op[9], op[10], op[11]);
            asm volatile("stmatrix.sync.aligned.m8n8.x2.shared.b16 [%0], {%1,%2};" ::"r"(oa + 96), "r"(op[12]), "r"(op[13]));
            fence_async_smem();
            __syncwarp();
            asm volatile("{\n.reg .pred p;\nelect.sync _|p, 0xffffffff;\n@p cp.async.bulk.tensor.3d.global.shared::cta.bulk_group [%0, {%2, %3, %4}], [%1];\n"
                         "cp.async.bulk.commit_group;\ncp.async.bulk.wait_group.read 0;\n}" ::"l"(&p.om), "r"(oc), "r"(56 * j), "r"(128 * r + 16 * warp), "r"(0) : "memory");
        }
        PROFC(26);
        bar_sync(1 + w, 128);
        if (wi == 0) warp_arrive(BAR(B_DONE));
        return;
    }
    helper_late(p, r, j, warp PROF_ARGS);
}

#undef act
typedef CUresult (*EncodeFn)(CUtensorMap*, CUtensorMapDataType, cuuint32_t, void*, const cuuint64_t*, const cuuint64_t*, const cuuint32_t*,
                             const cuuint32_t*, CUtensorMapInterleave, CUtensorMapSwizzle, CUtensorMapL2promotion, CUtensorMapFloatOOBfill);

static void make_map(EncodeFn fn, CUtensorMap* m, const void* ptr, uint64_t d0, uint64_t d1, uint64_t d2, uint64_t s1, uint64_t s2,
                     uint32_t b0, uint32_t b1, uint32_t b2, CUtensorMapSwizzle sw) {
    cuuint64_t dims[3] = {d0, d1, d2}, strides[2] = {s1, s2};
    cuuint32_t box[3] = {b0, b1, b2}, es[3] = {1, 1, 1};
    CUresult rc = fn(m, CU_TENSOR_MAP_DATA_TYPE_BFLOAT16, 3, (void*)ptr, dims, strides, box, es, CU_TENSOR_MAP_INTERLEAVE_NONE, sw,
                     CU_TENSOR_MAP_L2_PROMOTION_L2_128B, CU_TENSOR_MAP_FLOAT_OOB_FILL_NONE);
    (void)rc;
}

extern "C" void kernel_launch(void* const* d_in, const int* in_sizes, int n_in, void* d_out, int out_size) {
    (void)in_sizes; (void)n_in; (void)out_size;
    static EncodeFn fn = nullptr;
    static uint32_t* act_base = nullptr;
    if (!fn) {
        cudaDriverEntryPointQueryResult st;
        cudaGetDriverEntryPoint("cuTensorMapEncodeTiled", (void**)&fn, cudaEnableDefault, &st);
        void* a = nullptr;
        cudaGetSymbolAddress(&a, g_act);
        act_base = (uint32_t*)(((uintptr_t)a + 0xFFFFF) & ~(uintptr_t)0xFFFFF);
        cudaFuncSetAttribute(fused_block_kernel, cudaFuncAttributeMaxDynamicSharedMemorySize, SMEM_BYTES);
    }
    Params p;
    p.x = (const bf16*)d_in[0];
    const bf16* wqkv = (const bf16*)d_in[1];
    p.wqkv = wqkv;
    p.wop = (const bf16*)d_in[2];
    p.wg = (const bf16*)d_in[4];
    p.wu = (const bf16*)d_in[5];
    p.wd = (const bf16*)d_in[6];
    p.c = (const bf16*)d_in[7];
    p.wmod = (const bf16*)d_in[8];
    p.out = (bf16*)d_out;
    p.zero = 0;
    p.actb = act_base;
    make_map(fn, &p.wm, p.wmod, 2688, 448, 1, 5376, 5376 * 448, 16, 224, 1, CU_TENSOR_MAP_SWIZZLE_NONE);
    make_map(fn, &p.wm2, p.wmod, 2688, 448, 1, 5376, 5376 * 448, 32, 224, 1, CU_TENSOR_MAP_SWIZZLE_NONE);
    make_map(fn, &p.om, p.out, 448, 2048, 1, 896, 896 * 2048, 56, 16, 1, CU_TENSOR_MAP_SWIZZLE_NONE);
    make_map(fn, &p.xm, p.x, 448, 2048, 1, 896, 896 * 2048, 64, 128, 1, CU_TENSOR_MAP_SWIZZLE_128B);
    make_map(fn, &p.qkv, wqkv, 1344, 448, 1, 2688, 2688 * 448, 64, 224, 1, CU_TENSOR_MAP_SWIZZLE_128B);
    make_map(fn, &p.wo, p.wop, 448, 448, 1, 896, 896 * 448, 64, 224, 1, CU_TENSOR_MAP_SWIZZLE_128B);
    make_map(fn, &p.ga, p.wg, 64, 448, 28, 3584, 128, 64, 32, 2, CU_TENSOR_MAP_SWIZZLE_128B);
    make_map(fn, &p.ua, p.wu, 64, 448, 28, 3584, 128, 64, 32, 2, CU_TENSOR_MAP_SWIZZLE_128B);
    make_map(fn, &p.gb, p.wg, 64, 448, 28, 3584, 128, 64, 64, 1, CU_TENSOR_MAP_SWIZZLE_128B);
    make_map(fn, &p.ub, p.wu, 64, 448, 28, 3584, 128, 64, 64, 1, CU_TENSOR_MAP_SWIZZLE_128B);
    make_map(fn, &p.gc, p.wg, 32, 448, 56, 3584, 64, 32, 64, 1, CU_TENSOR_MAP_SWIZZLE_64B);
    make_map(fn, &p.uc, p.wu, 32, 448, 56, 3584, 64, 32, 64, 1, CU_TENSOR_MAP_SWIZZLE_64B);
    make_map(fn, &p.dn, p.wd, 8, 1792, 56, 896, 16, 8, 32, 7, CU_TENSOR_MAP_SWIZZLE_NONE);
    fused_block_kernel<<<GRID, 384, SMEM_BYTES>>>(p);
}
```

```cpp
#include <cuda_runtime.h>
#include <cuda_bf16.h>
#include <cuda.h>
#include <stdint.h>

typedef __nv_bfloat16 bf16;

__device__ __forceinline__ void wgmma_rl_56(float* d, uint32_t a0, uint32_t a1, uint32_t a2, uint32_t a3, uint64_t db, int sd) {
  asm volatile("{\n.reg .pred p;\nsetp.ne.b32 p, %33, 0;\n"
    "wgmma.mma_async.sync.aligned.m64n56k16.f32.bf16.bf16 {%0,%1,%2,%3,%4,%5,%6,%7,%8,%9,%10,%11,%12,%13,%14,%15,%16,%17,%18,%19,%20,%21,%22,%23,%24,%25,%26,%27}, {%28,%29,%30,%31}, %32, p, 1, 1, 1;\n}\n"
    : "+f"(d[0]),"+f"(d[1]),"+f"(d[2]),"+f"(d[3]),"+f"(d[4]),"+f"(d[5]),"+f"(d[6]),"+f"(d[7]),"+f"(d[8]),"+f"(d[9]),"+f"(d[10]),"+f"(d[11]),"+f"(d[12]),"+f"(d[13]),"+f"(d[14]),"+f"(d[15]),"+f"(d[16]),"+f"(d[17]),"+f"(d[18]),"+f"(d[19]),"+f"(d[20]),"+f"(d[21]),"+f"(d[22]),"+f"(d[23]),"+f"(d[24]),"+f"(d[25]),"+f"(d[26]),"+f"(d[27])
    : "r"(a0), "r"(a1), "r"(a2), "r"(a3), "l"(db), "r"(sd));
}
template<uint64_t CA, uint64_t CB> __device__ __forceinline__ void wgmma_ss_56(float* d, uint32_t da, uint32_t db, int sd) {
  asm volatile("{\n.reg .pred p;\n.reg .b64 a, b;\nsetp.ne.b32 p, %30, 0;\nmov.b64 a, {%28, %31};\nmov.b64 b, {%29, %32};\n"
    "wgmma.mma_async.sync.aligned.m64n56k16.f32.bf16.bf16 {%0,%1,%2,%3,%4,%5,%6,%7,%8,%9,%10,%11,%12,%13,%14,%15,%16,%17,%18,%19,%20,%21,%22,%23,%24,%25,%26,%27}, a, b, p, 1, 1, 0, 1;\n}\n"
    : "+f"(d[0]),"+f"(d[1]),"+f"(d[2]),"+f"(d[3]),"+f"(d[4]),"+f"(d[5]),"+f"(d[6]),"+f"(d[7]),"+f"(d[8]),"+f"(d[9]),"+f"(d[10]),"+f"(d[11]),"+f"(d[12]),"+f"(d[13]),"+f"(d[14]),"+f"(d[15]),"+f"(d[16]),"+f"(d[17]),"+f"(d[18]),"+f"(d[19]),"+f"(d[20]),"+f"(d[21]),"+f"(d[22]),"+f"(d[23]),"+f"(d[24]),"+f"(d[25]),"+f"(d[26]),"+f"(d[27])
    : "r"(da), "r"(db), "r"(sd), "n"((uint32_t)(CA >> 32)), "n"((uint32_t)(CB >> 32)));
}
__device__ __forceinline__ void wgmma_rl_256(float* d, uint32_t a0, uint32_t a1, uint32_t a2, uint32_t a3, uint64_t db, int sd) {
  asm volatile("{\n.reg .pred p;\nsetp.ne.b32 p, %133, 0;\n"
    "wgmma.mma_async.sync.aligned.m64n256k16.f32.bf16.bf16 {%0,%1,%2,%3,%4,%5,%6,%7,%8,%9,%10,%11,%12,%13,%14,%15,%16,%17,%18,%19,%20,%21,%22,%23,%24,%25,%26,%27,%28,%29,%30,%31,%32,%33,%34,%35,%36,%37,%38,%39,%40,%41,%42,%43,%44,%45,%46,%47,%48,%49,%50,%51,%52,%53,%54,%55,%56,%57,%58,%59,%60,%61,%62,%63,%64,%65,%66,%67,%68,%69,%70,%71,%72,%73,%74,%75,%76,%77,%78,%79,%80,%81,%82,%83,%84,%85,%86,%87,%88,%89,%90,%91,%92,%93,%94,%95,%96,%97,%98,%99,%100,%101,%102,%103,%104,%105,%106,%107,%108,%109,%110,%111,%112,%113,%114,%115,%116,%117,%118,%119,%120,%121,%122,%123,%124,%125,%126,%127}, {%128,%129,%130,%131}, %132, p, 1, 1, 1;\n}\n"
    : "+f"(d[0]),"+f"(d[1]),"+f"(d[2]),"+f"(d[3]),"+f"(d[4]),"+f"(d[5]),"+f"(d[6]),"+f"(d[7]),"+f"(d[8]),"+f"(d[9]),"+f"(d[10]),"+f"(d[11]),"+f"(d[12]),"+f"(d[13]),"+f"(d[14]),"+f"(d[15]),"+f"(d[16]),"+f"(d[17]),"+f"(d[18]),"+f"(d[19]),"+f"(d[20]),"+f"(d[21]),"+f"(d[22]),"+f"(d[23]),"+f"(d[24]),"+f"(d[25]),"+f"(d[26]),"+f"(d[27]),"+f"(d[28]),"+f"(d[29]),"+f"(d[30]),"+f"(d[31]),"+f"(d[32]),"+f"(d[33]),"+f"(d[34]),"+f"(d[35]),"+f"(d[36]),"+f"(d[37]),"+f"(d[38]),"+f"(d[39]),"+f"(d[40]),"+f"(d[41]),"+f"(d[42]),"+f"(d[43]),"+f"(d[44]),"+f"(d[45]),"+f"(d[46]),"+f"(d[47]),"+f"(d[48]),"+f"(d[49]),"+f"(d[50]),"+f"(d[51]),"+f"(d[52]),"+f"(d[53]),"+f"(d[54]),"+f"(d[55]),"+f"(d[56]),"+f"(d[57]),"+f"(d[58]),"+f"(d[59]),"+f"(d[60]),"+f"(d[61]),"+f"(d[62]),"+f"(d[63]),"+f"(d[64]),"+f"(d[65]),"+f"(d[66]),"+f"(d[67]),"+f"(d[68]),"+f"(d[69]),"+f"(d[70]),"+f"(d[71]),"+f"(d[72]),"+f"(d[73]),"+f"(d[74]),"+f"(d[75]),"+f"(d[76]),"+f"(d[77]),"+f"(d[78]),"+f"(d[79]),"+f"(d[80]),"+f"(d[81]),"+f"(d[82]),"+f"(d[83]),"+f"(d[84]),"+f"(d[85]),"+f"(d[86]),"+f"(d[87]),"+f"(d[88]),"+f"(d[89]),"+f"(d[90]),"+f"(d[91]),"+f"(d[92]),"+f"(d[93]),"+f"(d[94]),"+f"(d[95]),"+f"(d[96]),"+f"(d[97]),"+f"(d[98]),"+f"(d[99]),"+f"(d[100]),"+f"(d[101]),"+f"(d[102]),"+f"(d[103]),"+f"(d[104]),"+f"(d[105]),"+f"(d[106]),"+f"(d[107]),"+f"(d[108]),"+f"(d[109]),"+f"(d[110]),"+f"(d[111]),"+f"(d[112]),"+f"(d[113]),"+f"(d[114]),"+f"(d[115]),"+f"(d[116]),"+f"(d[117]),"+f"(d[118]),"+f"(d[119]),"+f"(d[120]),"+f"(d[121]),"+f"(d[122]),"+f"(d[123]),"+f"(d[124]),"+f"(d[125]),"+f"(d[126]),"+f"(d[127])
    : "r"(a0), "r"(a1), "r"(a2), "r"(a3), "l"(db), "r"(sd));
}
template<uint64_t CA, uint64_t CB> __device__ __forceinline__ void wgmma_ss_128(float* d, uint32_t da, uint32_t db, int sd) {
  asm volatile("{\n.reg .pred p;\n.reg .b64 a, b;\nsetp.ne.b32 p, %66, 0;\nmov.b64 a, {%64, %67};\nmov.b64 b, {%65, %68};\n"
    "wgmma.mma_async.sync.aligned.m64n128k16.f32.bf16.bf16 {%0,%1,%2,%3,%4,%5,%6,%7,%8,%9,%10,%11,%12,%13,%14,%15,%16,%17,%18,%19,%20,%21,%22,%23,%24,%25,%26,%27,%28,%29,%30,%31,%32,%33,%34,%35,%36,%37,%38,%39,%40,%41,%42,%43,%44,%45,%46,%47,%48,%49,%50,%51,%52,%53,%54,%55,%56,%57,%58,%59,%60,%61,%62,%63}, a, b, p, 1, 1, 0, 1;\n}\n"
    : "+f"(d[0]),"+f"(d[1]),"+f"(d[2]),"+f"(d[3]),"+f"(d[4]),"+f"(d[5]),"+f"(d[6]),"+f"(d[7]),"+f"(d[8]),"+f"(d[9]),"+f"(d[10]),"+f"(d[11]),"+f"(d[12]),"+f"(d[13]),"+f"(d[14]),"+f"(d[15]),"+f"(d[16]),"+f"(d[17]),"+f"(d[18]),"+f"(d[19]),"+f"(d[20]),"+f"(d[21]),"+f"(d[22]),"+f"(d[23]),"+f"(d[24]),"+f"(d[25]),"+f"(d[26]),"+f"(d[27]),"+f"(d[28]),"+f"(d[29]),"+f"(d[30]),"+f"(d[31]),"+f"(d[32]),"+f"(d[33]),"+f"(d[34]),"+f"(d[35]),"+f"(d[36]),"+f"(d[37]),"+f"(d[38]),"+f"(d[39]),"+f"(d[40]),"+f"(d[41]),"+f"(d[42]),"+f"(d[43]),"+f"(d[44]),"+f"(d[45]),"+f"(d[46]),"+f"(d[47]),"+f"(d[48]),"+f"(d[49]),"+f"(d[50]),"+f"(d[51]),"+f"(d[52]),"+f"(d[53]),"+f"(d[54]),"+f"(d[55]),"+f"(d[56]),"+f"(d[57]),"+f"(d[58]),"+f"(d[59]),"+f"(d[60]),"+f"(d[61]),"+f"(d[62]),"+f"(d[63])
    : "r"(da), "r"(db), "r"(sd), "n"((uint32_t)(CA >> 32)), "n"((uint32_t)(CB >> 32)));
}
template<uint64_t CA, uint64_t CB> __device__ __forceinline__ void wgmma_ss_64(float* d, uint32_t da, uint32_t db, int sd) {
  asm volatile("{\n.reg .pred p;\n.reg .b64 a, b;\nsetp.ne.b32 p, %34, 0;\nmov.b64 a, {%32, %35};\nmov.b64 b, {%33, %36};\n"
    "wgmma.mma_async.sync.aligned.m64n64k16.f32.bf16.bf16 {%0,%1,%2,%3,%4,%5,%6,%7,%8,%9,%10,%11,%12,%13,%14,%15,%16,%17,%18,%19,%20,%21,%22,%23,%24,%25,%26,%27,%28,%29,%30,%31}, a, b, p, 1, 1, 0, 1;\n}\n"
    : "+f"(d[0]),"+f"(d[1]),"+f"(d[2]),"+f"(d[3]),"+f"(d[4]),"+f"(d[5]),"+f"(d[6]),"+f"(d[7]),"+f"(d[8]),"+f"(d[9]),"+f"(d[10]),"+f"(d[11]),"+f"(d[12]),"+f"(d[13]),"+f"(d[14]),"+f"(d[15]),"+f"(d[16]),"+f"(d[17]),"+f"(d[18]),"+f"(d[19]),"+f"(d[20]),"+f"(d[21]),"+f"(d[22]),"+f"(d[23]),"+f"(d[24]),"+f"(d[25]),"+f"(d[26]),"+f"(d[27]),"+f"(d[28]),"+f"(d[29]),"+f"(d[30]),"+f"(d[31])
    : "r"(da), "r"(db), "r"(sd), "n"((uint32_t)(CA >> 32)), "n"((uint32_t)(CB >> 32)));
}
template<uint64_t CA, uint64_t CB> __device__ __forceinline__ void wgmma_ss_112(float* d, uint32_t da, uint32_t db, int sd) {
  asm volatile("{\n.reg .pred p;\n.reg .b64 a, b;\nsetp.ne.b32 p, %58, 0;\nmov.b64 a, {%56, %59};\nmov.b64 b, {%57, %60};\n"
    "wgmma.mma_async.sync.aligned.m64n112k16.f32.bf16.bf16 {%0,%1,%2,%3,%4,%5,%6,%7,%8,%9,%10,%11,%12,%13,%14,%15,%16,%17,%18,%19,%20,%21,%22,%23,%24,%25,%26,%27,%28,%29,%30,%31,%32,%33,%34,%35,%36,%37,%38,%39,%40,%41,%42,%43,%44,%45,%46,%47,%48,%49,%50,%51,%52,%53,%54,%55}, a, b, p, 1, 1, 0, 1;\n}\n"
    : "+f"(d[0]),"+f"(d[1]),"+f"(d[2]),"+f"(d[3]),"+f"(d[4]),"+f"(d[5]),"+f"(d[6]),"+f"(d[7]),"+f"(d[8]),"+f"(d[9]),"+f"(d[10]),"+f"(d[11]),"+f"(d[12]),"+f"(d[13]),"+f"(d[14]),"+f"(d[15]),"+f"(d[16]),"+f"(d[17]),"+f"(d[18]),"+f"(d[19]),"+f"(d[20]),"+f"(d[21]),"+f"(d[22]),"+f"(d[23]),"+f"(d[24]),"+f"(d[25]),"+f"(d[26]),"+f"(d[27]),"+f"(d[28]),"+f"(d[29]),"+f"(d[30]),"+f"(d[31]),"+f"(d[32]),"+f"(d[33]),"+f"(d[34]),"+f"(d[35]),"+f"(d[36]),"+f"(d[37]),"+f"(d[38]),"+f"(d[39]),"+f"(d[40]),"+f"(d[41]),"+f"(d[42]),"+f"(d[43]),"+f"(d[44]),"+f"(d[45]),"+f"(d[46]),"+f"(d[47]),"+f"(d[48]),"+f"(d[49]),"+f"(d[50]),"+f"(d[51]),"+f"(d[52]),"+f"(d[53]),"+f"(d[54]),"+f"(d[55])
    : "r"(da), "r"(db), "r"(sd), "n"((uint32_t)(CA >> 32)), "n"((uint32_t)(CB >> 32)));
}
__device__ __forceinline__ void wgmma_rl_112(float* d, uint32_t a0, uint32_t a1, uint32_t a2, uint32_t a3, uint64_t db, int sd) {
  asm volatile("{\n.reg .pred p;\nsetp.ne.b32 p, %61, 0;\n"
    "wgmma.mma_async.sync.aligned.m64n112k16.f32.bf16.bf16 {%0,%1,%2,%3,%4,%5,%6,%7,%8,%9,%10,%11,%12,%13,%14,%15,%16,%17,%18,%19,%20,%21,%22,%23,%24,%25,%26,%27,%28,%29,%30,%31,%32,%33,%34,%35,%36,%37,%38,%39,%40,%41,%42,%43,%44,%45,%46,%47,%48,%49,%50,%51,%52,%53,%54,%55}, {%56,%57,%58,%59}, %60, p, 1, 1, 1;\n}\n"
    : "+f"(d[0]),"+f"(d[1]),"+f"(d[2]),"+f"(d[3]),"+f"(d[4]),"+f"(d[5]),"+f"(d[6]),"+f"(d[7]),"+f"(d[8]),"+f"(d[9]),"+f"(d[10]),"+f"(d[11]),"+f"(d[12]),"+f"(d[13]),"+f"(d[14]),"+f"(d[15]),"+f"(d[16]),"+f"(d[17]),"+f"(d[18]),"+f"(d[19]),"+f"(d[20]),"+f"(d[21]),"+f"(d[22]),"+f"(d[23]),"+f"(d[24]),"+f"(d[25]),"+f"(d[26]),"+f"(d[27]),"+f"(d[28]),"+f"(d[29]),"+f"(d[30]),"+f"(d[31]),"+f"(d[32]),"+f"(d[33]),"+f"(d[34]),"+f"(d[35]),"+f"(d[36]),"+f"(d[37]),"+f"(d[38]),"+f"(d[39]),"+f"(d[40]),"+f"(d[41]),"+f"(d[42]),"+f"(d[43]),"+f"(d[44]),"+f"(d[45]),"+f"(d[46]),"+f"(d[47]),"+f"(d[48]),"+f"(d[49]),"+f"(d[50]),"+f"(d[51]),"+f"(d[52]),"+f"(d[53]),"+f"(d[54]),"+f"(d[55])
    : "r"(a0), "r"(a1), "r"(a2), "r"(a3), "l"(db), "r"(sd));
}

constexpr int DM = 448;
constexpr int NCTA = 128;
#define MAPPING 1
#define GRID 128
#define PINGPONG 0
#define WIN 6
#define WIN_END 25
#define UNR_B 1
#define UNR_C 1
constexpr int kB = UNR_B, kC = UNR_C;
#define LIKELY(x) __builtin_expect(!!(x), 1)
#define PACE 1
#define PACE_END 6
#define GEMV_AT 1
#define NPRE 14
#define ATT_OFF 0
#define ATT_WG 1
#define XFIRST 7
#define KDELAY 0
#define KEARLY 1
#define MAP_S 4
constexpr int SPIN_LIMIT = 1 << 22;

constexpr uint32_t OFF_X = 0, OFF_Y = 114688, OFF_MISC = 229376, SMEM_BYTES = 232448;
constexpr uint32_t Y_VR = 0, Y_K = 28672, Y_KOWN = 57344, Y_VOWN = 71680, Y_Q = 86016;
constexpr uint32_t HALF = 57344;
constexpr uint32_t X_STAT = 49152;
constexpr uint32_t OUT_STAGE = 16384;
constexpr uint32_t M_BAR = OFF_MISC;
constexpr uint32_t M_ST = OFF_MISC + 512;
constexpr uint32_t M_G = OFF_MISC + 2304;
constexpr uint32_t M_EPOCH = OFF_MISC + 3040;
enum { B_XFULL = 0, B_FULLK = 7, B_FULLV = 8, B_FULLQ, B_KRFULL, B_VRFULL, B_WOFULL, B_XCH, B_MOD1 = 15, B_FULL = 16, B_WMFULL = 30,
       B_EMPTY = 32, B_XFREE = B_EMPTY + 12, B_GEMV, B_PEER,
       B_PUB = 47,
       B_WMFREE = 56, B_HRDY, B_GFULL = B_HRDY + 3, B_DONE = 31, B_DUMMY = B_GEMV };

__device__ uint32_t g_ticket;
__device__ __align__(128) uint32_t g_mod[8 * 6 * DM];
__device__ __align__(128) uint32_t g_flag[144 * 128];
constexpr int RB_WORDS = 276480, RB_KV = 0, RB_O = 57344, RB_X1 = 86016, RB_H2 = 143360, RB_ST = 258048, RB_O2 = 262144;
__device__ __align__(128) uint32_t g_act[16 * RB_WORDS];
__device__ __align__(128) uint32_t g_wd[56 * 4 * 1792];
#define PROFH(id)
#define PROFH1(id)
#define PROFC(id)

struct alignas(64) Params {
    CUtensorMap wm, wm2, om, xm, qkv, wo, ga, ua, gb, ub, gc, uc, dn;
    const bf16 *x, *c, *wqkv, *wmod, *wg, *wu, *wd, *wop;
    bf16* out;
    uint32_t* actb;
    uint32_t zero;
};

__device__ __forceinline__ void mbar_init(uint32_t bar, int cnt) { asm volatile("mbarrier.init.shared::cta.b64 [%0], %1;" ::"r"(bar), "r"(cnt) : "memory"); }
__device__ __forceinline__ void mbar_expect_tx(uint32_t bar, uint32_t bytes) { asm volatile("mbarrier.arrive.expect_tx.shared::cta.b64 _, [%0], %1;" ::"r"(bar), "r"(bytes) : "memory"); }
__device__ __forceinline__ void mbar_arrive(uint32_t bar) { asm volatile("mbarrier.arrive.shared::cta.b64 _, [%0];" ::"r"(bar) : "memory"); }
__device__ __forceinline__ void mbar_wait(uint32_t bar, uint32_t parity) {
    uint32_t ok; int n = 0;
    do {
        asm volatile("{\n.reg .pred p;\nmbarrier.try_wait.parity.shared::cta.b64 p, [%1], %2;\nselp.u32 %0, 1, 0, p;\n}" : "=r"(ok) : "r"(bar), "r"(parity) : "memory");
        if (++n > SPIN_LIMIT) __trap();
    } while (!ok);
}
__device__ __forceinline__ void mbar_wait_c(uint32_t bar, uint32_t parity) {
    asm volatile("{\n.reg .pred p;\nWL:\nmbarrier.try_wait.parity.shared::cta.b64 p, [%0], %1, 0x989680;\n@!p bra WL;\n}" ::"r"(bar), "r"(parity) : "memory");
}
__device__ __forceinline__ void mbar_wait_cluster(uint32_t bar, uint32_t parity) {
    asm volatile("{\n.reg .pred p;\nWL:\nmbarrier.try_wait.parity.acquire.cluster.shared::cta.b64 p, [%0], %1, 0x989680;\n@!p bra WL;\n}" ::"r"(bar), "r"(parity) : "memory");
}
__device__ __forceinline__ void warp_arrive(uint32_t bar) {
    __syncwarp();
    asm volatile("{\n.reg .pred p;\nelect.sync _|p, 0xffffffff;\n@p mbarrier.arrive.shared::cta.b64 _, [%0];\n}" ::"r"(bar) : "memory");
}
__device__ __forceinline__ int opaque(int v) { return __shfl_sync(~0u, v, 0); }
__device__ __forceinline__ int fresh_tid() { int v; asm volatile("mov.u32 %0, %%tid.x;" : "=r"(v)); return v; }
__device__ __forceinline__ void bar_sync(int id, int n) { asm volatile("bar.sync %0, %1;" ::"r"(id), "r"(n) : "memory"); }
__device__ __forceinline__ void bar_arrive(int id, int n) { asm volatile("bar.arrive %0, %1;" ::"r"(id), "r"(n) : "memory"); }
__device__ __forceinline__ void fence_async_smem() { asm volatile("fence.proxy.async.shared::cta;" ::: "memory"); }
__device__ __forceinline__ void fence_async_global() { asm volatile("fence.proxy.async.global;" ::: "memory"); }
__device__ __forceinline__ void fence_gpu() { asm volatile("fence.release.gpu;" ::: "memory"); }
__device__ __forceinline__ void tma3(uint32_t dst, const CUtensorMap* m, int c0, int c1, int c2, uint32_t bar) {
    asm volatile("cp.async.bulk.tensor.3d.shared::cluster.global.mbarrier::complete_tx::bytes [%0], [%1, {%3, %4, %5}], [%2];"
                 ::"r"(dst), "l"(m), "r"(bar), "r"(c0), "r"(c1), "r"(c2) : "memory");
}
__device__ __forceinline__ void bulk_load(uint32_t dst, const void* src, uint32_t bytes, uint32_t bar) {
    asm volatile("cp.async.bulk.shared::cluster.global.mbarrier::complete_tx::bytes [%0], [%1], %2, [%3];" ::"r"(dst), "l"(src), "r"(bytes), "r"(bar) : "memory");
}
__device__ __forceinline__ void expect_e(uint32_t bar, uint32_t bytes) {
    asm volatile("{\n.reg .pred p;\nelect.sync _|p, 0xffffffff;\n@p mbarrier.arrive.expect_tx.shared::cta.b64 _, [%0], %1;\n}" ::"r"(bar), "r"(bytes) : "memory");
}
__device__ __forceinline__ void tma3_e(uint32_t dst, const CUtensorMap* m, int c0, int c1, int c2, uint32_t bar) {
    asm volatile("{\n.reg .pred p;\nelect.sync _|p, 0xffffffff;\n@p cp.async.bulk.tensor.3d.shared::cluster.global.mbarrier::complete_tx::bytes [%0], [%1, {%3, %4, %5}], [%2];\n}"
                 ::"r"(dst), "l"(m), "r"(bar), "r"(c0), "r"(c1), "r"(c2) : "memory");
}
__device__ __forceinline__ void bulk_e(uint32_t dst, const void* src, uint32_t bytes, uint32_t bar) {
    asm volatile("{\n.reg .pred p;\nelect.sync _|p, 0xffffffff;\n@p cp.async.bulk.shared::cluster.global.mbarrier::complete_tx::bytes [%0], [%1], %2, [%3];\n}"
                 ::"r"(dst), "l"(src), "r"(bytes), "r"(bar) : "memory");
}
__device__ __forceinline__ void init_e(uint32_t bar, int cnt) {
    asm volatile("{\n.reg .pred p;\nelect.sync _|p, 0xffffffff;\n@p mbarrier.init.shared::cta.b64 [%0], %1;\n}" ::"r"(bar), "r"(cnt) : "memory");
}
__device__ __forceinline__ void l2_prefetch_e(const void* src, uint32_t bytes) {
    asm volatile("{\n.reg .pred p;\nelect.sync _|p, 0xffffffff;\n@p cp.async.bulk.prefetch.L2.global [%0], %1;\n}" ::"l"(src), "r"(bytes) : "memory");
}
__device__ __forceinline__ uint32_t ld_relaxed(const uint32_t* p) { uint32_t v; asm volatile("ld.relaxed.gpu.global.u32 %0, [%1];" : "=r"(v) : "l"(p) : "memory"); return v; }
__device__ __forceinline__ void st_relaxed(uint32_t* p, uint32_t v) { asm volatile("st.relaxed.gpu.global.u32 [%0], %1;" ::"l"(p), "r"(v) : "memory"); }
__device__ __forceinline__ uint4 ld_relaxed4(const uint4* p) { uint4 v; asm volatile("ld.relaxed.gpu.global.v4.u32 {%0,%1,%2,%3}, [%4];" : "=r"(v.x), "=r"(v.y), "=r"(v.z), "=r"(v.w) : "l"(p) : "memory"); return v; }
__device__ __forceinline__ void st_relaxed4(uint4* p, uint4 v) { asm volatile("st.relaxed.gpu.global.v4.u32 [%0], {%1,%2,%3,%4};" ::"l"(p), "r"(v.x), "r"(v.y), "r"(v.z), "r"(v.w) : "memory"); }
__device__ __forceinline__ uint4 ldg_nc4(const void* p) { uint4 v; asm volatile("ld.global.nc.L1::no_allocate.v4.u32 {%0,%1,%2,%3}, [%4];" : "=r"(v.x), "=r"(v.y), "=r"(v.z), "=r"(v.w) : "l"(p)); return v; }
__device__ __forceinline__ uint32_t ldg_nc(const void* p) { uint32_t v; asm volatile("ld.global.nc.u32 %0, [%1];" : "=r"(v) : "l"(p)); return v; }
__device__ __forceinline__ uint32_t ld_acquire(const uint32_t* p) { uint32_t v; asm volatile("ld.acquire.gpu.global.u32 %0, [%1];" : "=r"(v) : "l"(p) : "memory"); return v; }
__device__ __forceinline__ uint4 lds4(uint32_t a) { uint4 v; asm volatile("ld.shared.v4.u32 {%0,%1,%2,%3}, [%4];" : "=r"(v.x), "=r"(v.y), "=r"(v.z), "=r"(v.w) : "r"(a) : "memory"); return v; }
__device__ __forceinline__ float2 lds2f(uint32_t a) { float2 v; asm volatile("ld.shared.v2.f32 {%0,%1}, [%2];" : "=f"(v.x), "=f"(v.y) : "r"(a) : "memory"); return v; }
__device__ __forceinline__ uint32_t lds1(uint32_t a) { uint32_t v; asm volatile("ld.shared.u32 %0, [%1];" : "=r"(v) : "r"(a) : "memory"); return v; }
__device__ __forceinline__ void sts4(uint32_t a, uint4 v) { asm volatile("st.shared.v4.u32 [%0], {%1,%2,%3,%4};" ::"r"(a), "r"(v.x), "r"(v.y), "r"(v.z), "r"(v.w) : "memory"); }
__device__ __forceinline__ void sts2(uint32_t a, uint32_t x, uint32_t y) { asm volatile("st.shared.v2.u32 [%0], {%1,%2};" ::"r"(a), "r"(x), "r"(y) : "memory"); }
__device__ __forceinline__ void sts1(uint32_t a, uint32_t v) { asm volatile("st.shared.u32 [%0], %1;" ::"r"(a), "r"(v) : "memory"); }
__device__ __forceinline__ void stsm4(uint32_t a, uint32_t r0, uint32_t r1, uint32_t r2, uint32_t r3) {
    asm volatile("stmatrix.sync.aligned.m8n8.x4.shared.b16 [%0], {%1,%2,%3,%4};" ::"r"(a), "r"(r0), "r"(r1), "r"(r2), "r"(r3));
}
__device__ __forceinline__ uint32_t pack2(float lo, float hi) { uint32_t r; asm("cvt.rn.bf16x2.f32 %0, %1, %2;" : "=r"(r) : "f"(hi), "f"(lo)); return r; }
__device__ __forceinline__ uint32_t pack2_relu(float lo, float hi) { uint32_t r; asm("cvt.rn.relu.bf16x2.f32 %0, %1, %2;" : "=r"(r) : "f"(hi), "f"(lo)); return r; }
__device__ __forceinline__ uint32_t hfma2(uint32_t a, uint32_t b, uint32_t c) { uint32_t r; asm("fma.rn.bf16x2 %0, %1, %2, %3;" : "=r"(r) : "r"(a), "r"(b), "r"(c)); return r; }
__device__ __forceinline__ uint32_t hmul2(uint32_t a, uint32_t b) { uint32_t r; asm("mul.rn.bf16x2 %0, %1, %2;" : "=r"(r) : "r"(a), "r"(b)); return r; }
__device__ __forceinline__ float bf_lo(uint32_t v) { return __uint_as_float(v << 16); }
__device__ __forceinline__ float bf_hi(uint32_t v) { return __uint_as_float(v & 0xFFFF0000u); }
__device__ __forceinline__ float bf_round(float v) { return bf_lo(pack2(v, 0.f)); }
__device__ __forceinline__ float ex2(float x) { float r; asm("ex2.approx.ftz.f32 %0, %1;" : "=f"(r) : "f"(x)); return r; }
__device__ __forceinline__ void mma16816(float* d, uint32_t a0, uint32_t a1, uint32_t a2, uint32_t a3, uint32_t b0, uint32_t b1) {
    asm("mma.sync.aligned.m16n8k16.row.col.f32.bf16.bf16.f32 {%0,%1,%2,%3}, {%4,%5,%6,%7}, {%8,%9}, {%0,%1,%2,%3};"
        : "+f"(d[0]), "+f"(d[1]), "+f"(d[2]), "+f"(d[3]) : "r"(a0), "r"(a1), "r"(a2), "r"(a3), "r"(b0), "r"(b1));
}
__device__ __forceinline__ void mma16816_first(float* d, uint32_t a0, uint32_t a1, uint32_t a2, uint32_t a3, uint32_t b0, uint32_t b1) {
    asm volatile("mma.sync.aligned.m16n8k16.row.col.f32.bf16.bf16.f32 {%0,%1,%2,%3}, {%4,%5,%6,%7}, {%8,%9}, {%10,%10,%10,%10};"
        : "=f"(d[0]), "=f"(d[1]), "=f"(d[2]), "=f"(d[3]) : "r"(a0), "r"(a1), "r"(a2), "r"(a3), "r"(b0), "r"(b1), "f"(0.f));
}
__device__ __forceinline__ void mma16816_v(float* d, uint32_t a0, uint32_t a1, uint32_t a2, uint32_t a3, uint32_t b0, uint32_t b1) {
    asm volatile("mma.sync.aligned.m16n8k16.row.col.f32.bf16.bf16.f32 {%0,%1,%2,%3}, {%4,%5,%6,%7}, {%8,%9}, {%0,%1,%2,%3};"
        : "+f"(d[0]), "+f"(d[1]), "+f"(d[2]), "+f"(d[3]) : "r"(a0), "r"(a1), "r"(a2), "r"(a3), "r"(b0), "r"(b1));
}
__device__ __forceinline__ void mma1688(float* d, uint32_t a0, uint32_t a1, uint32_t b0) {
    asm("mma.sync.aligned.m16n8k8.row.col.f32.bf16.bf16.f32 {%0,%1,%2,%3}, {%4,%5}, {%6}, {%0,%1,%2,%3};"
        : "+f"(d[0]), "+f"(d[1]), "+f"(d[2]), "+f"(d[3]) : "r"(a0), "r"(a1), "r"(b0));
}
__device__ __forceinline__ void ldsm4(uint32_t a, uint32_t* r) {
    asm volatile("ldmatrix.sync.aligned.m8n8.x4.shared.b16 {%0,%1,%2,%3}, [%4];" : "=r"(r[0]), "=r"(r[1]), "=r"(r[2]), "=r"(r[3]) : "r"(a));
}
__device__ __forceinline__ void ldsm4t(uint32_t a, uint32_t* r) {
    asm volatile("ldmatrix.sync.aligned.m8n8.x4.trans.shared.b16 {%0,%1,%2,%3}, [%4];" : "=r"(r[0]), "=r"(r[1]), "=r"(r[2]), "=r"(r[3]) : "r"(a));
}
__device__ __forceinline__ uint32_t nz(uint32_t v) { uint32_t r; asm("max.u32 %0, %1, 1;" : "=r"(r) : "r"(v)); return r; }
__device__ __forceinline__ float rcp(float x) { float r; asm("rcp.approx.ftz.f32 %0, %1;" : "=f"(r) : "f"(x)); return r; }
__device__ __forceinline__ uint2 ld_relaxed2(const void* p) { uint2 v; asm volatile("ld.relaxed.gpu.global.v2.u32 {%0,%1}, [%2];" : "=r"(v.x), "=r"(v.y) : "l"(p) : "memory"); return v; }
__device__ __forceinline__ void st_relaxed2(void* p, uint32_t x, uint32_t y) { asm volatile("st.relaxed.gpu.global.v2.u32 [%0], {%1,%2};" ::"l"(p), "r"(max(x, 1u)), "r"(max(y, 1u)) : "memory"); }
__host__ __device__ constexpr uint64_t dconst(uint32_t lbo, uint32_t sbo, uint32_t swz) {
    return ((uint64_t)(lbo >> 4) << 16) | ((uint64_t)(sbo >> 4) << 32) | ((uint64_t)swz << 62);
}
__device__ __forceinline__ uint32_t mkdesc(uint32_t addr, uint64_t c) { return (uint32_t)c | ((addr & 0x3FFFF) >> 4); }
#define WG_FENCE() asm volatile("wgmma.fence.sync.aligned;" ::: "memory")
#define WG_COMMIT() asm volatile("wgmma.commit_group.sync.aligned;" ::: "memory")
#define WG_WAIT(n) asm volatile("wgmma.wait_group.sync.aligned %0;" ::"n"(n) : "memory")
template <int N> __device__ __forceinline__ void reg_fence(float* d) {
#pragma unroll
    for (int i = 0; i < N; i++) asm volatile("" : "+f"(d[i])::"memory");
}
template <int N> __device__ __forceinline__ void reg_def(float* d) {
#pragma unroll
    for (int i = 0; i < N; i++) asm volatile("" : "=f"(d[i]));
}
template <int N> __device__ __forceinline__ void reg_def(uint32_t* d) {
#pragma unroll
    for (int i = 0; i < N; i++) asm volatile("" : "=r"(d[i]));
}
__device__ __forceinline__ bool is_unset(uint4 v) { return min(min(v.x, v.y), min(v.z, v.w)) == 0u; }
__device__ __forceinline__ uint4 nz4(uint32_t a, uint32_t b, uint32_t c, uint32_t d) { return make_uint4(max(a, 1u), max(b, 1u), max(c, 1u), max(d, 1u)); }
__device__ __forceinline__ void wait_flags(const uint32_t* p, uint32_t target, uint32_t mask) {
    int n = 0;
    while (~__ballot_sync(~0u, (int)(ld_relaxed(p) - target) >= 0) & mask) { if (++n > SPIN_LIMIT) __trap(); }
    asm volatile("fence.acquire.gpu;" ::: "memory");
}
__device__ __forceinline__ float silu_bf(uint32_t cbits) {
    const float c = __uint_as_float(cbits << 16);
    return bf_round(__fdividef(c, 1.f + fminf(ex2(-1.4426950408889634f * c), 1e30f)));
}
__device__ __forceinline__ void gemv_part(uint32_t wmbuf, int wp, int lane) {
    const uint32_t wa = wmbuf + wp * 512 + (8 * (lane >> 4) + (lane & 7)) * 32 + ((lane >> 3) & 1) * 16;
    float d[4] = {};
#pragma unroll
    for (int i = 0; i < 4; i++) {
        uint32_t A[4];
        const float2 v = lds2f(wmbuf + 28672 + (wp + 8 * i) * 32 + (lane & 3) * 8);
        ldsm4t(wa + (i < 3 || wp < 4 ? i : 0) * 4096, A);
        mma16816(d, A[0], A[1], A[2], A[3], __float_as_uint(v.x), __float_as_uint(v.y));
    }
    if ((lane & 3) == 0) {
        sts1(wmbuf + 29696 + (wp * 16 + (lane >> 2)) * 4, __float_as_uint(d[0]));
        sts1(wmbuf + 29696 + (wp * 16 + 8 + (lane >> 2)) * 4, __float_as_uint(d[2]));
    }
}
__device__ __forceinline__ uint32_t mod_word(float v, int col, uint32_t target) {
    v = bf_round(v);
    if ((col >= DM && col < 2 * DM) || (col >= 4 * DM && col < 5 * DM)) v += 1.f;
    return (pack2(v, 0.f) << 16) | (target & 0xFFFFu);
}
__device__ __forceinline__ const uint4* mod_src(int i, int r, int j, bool p2) {
    i = min(i, p2 ? 251 : 223);
    return (const uint4*)g_mod + (r & 7) * (6 * DM / 4) + (i < 224 ? (p2 ? 336 : 0) + i : (i < 238 ? 14 * j + i : 14 * j + i + 322));
}
__device__ __forceinline__ void mod_store(uint32_t sb, uint4 v, const uint4* src, int i) {
    const uint32_t tag = lds1(sb + M_EPOCH) + 1;
    while (__any_sync(~0u, (((v.x ^ tag) | (v.y ^ tag) | (v.z ^ tag) | (v.w ^ tag)) & 0xFFFFu) != 0u)) v = ld_relaxed4(src);
    if (i < 224) {
        const int isc = i >= 112, c4 = i - 112 * isc;
        const uint32_t a = sb + M_ST + (c4 >> 2) * 64 + (c4 & 1) * 32 + (c4 & 2) * 4 + (isc ? 0 : 4);
        sts1(a, __byte_perm(v.x, v.y, 0x7632));
        sts1(a + 16, __byte_perm(v.z, v.w, 0x7632));
    } else if (i < 252) {
        sts4(sb + M_G + (i - 224) * 16, make_uint4(v.x & 0xFFFF0000u, v.y & 0xFFFF0000u, v.z & 0xFFFF0000u, v.w & 0xFFFF0000u));
    }
}
__device__ __forceinline__ int pass_f(int fs, int ps) { return 224 * fs + ((fs & 1) ? (ps == 0 ? 96 : ps == 1 ? 32 : 0) : (ps == 0 ? 0 : ps == 1 ? 128 : 192)); }
__device__ __forceinline__ constexpr uint32_t slot_off(int l) { return l * 16384; }
__device__ __forceinline__ constexpr int g1_slot(int s) { return s % 7; }
__device__ __noinline__ void x1_fix(const uint32_t* g, uint32_t sa, int s) {
#pragma unroll 1
    for (int k = 4 * s; k < 4 * s + 4;) {
        const uint4 v = ld_relaxed4((const uint4*)(g + k * 256));
        sts4(sa + k * 1024, v);
        k += 2 * __all_sync(~0u, min(min(v.x, v.y), min(v.z, v.w)) != 0u);
    }
    __syncwarp();
}
__device__ __forceinline__ void tile_check(const uint32_t* g, uint32_t sa) {
    uint32_t mn = ~0u;
#pragma unroll
    for (int k = 0; k < 14; k++) { const uint4 v = lds4(sa + k * 2048); mn = min(min(mn, v.x), min(min(v.y, v.z), v.w)); }
    if (__any_sync(~0u, mn == 0u)) {
#pragma unroll 1
        for (int k = 0; k < 14;) {
            const uint4 v = ld_relaxed4((const uint4*)(g + k * 512));
            sts4(sa + k * 2048, v);
            k += __all_sync(~0u, min(min(v.x, v.y), min(v.z, v.w)) != 0u);
        }
        fence_async_smem();
    }
}
__device__ __forceinline__ void ln_coeffs(float mean, float msq, uint32_t& r2, uint32_t& n2) {
    const float rs = bf_round(rsqrtf(fmaxf(msq - mean * mean, 0.f) + 1e-5f));
    r2 = pack2(rs, rs);
    n2 = pack2(-mean * rs, -mean * rs);
}

#define LOADW bulk_e(dst, g_wd + (size_t)((f >> 5) * 4 + nq) * 1792, 7168, bar);
template <int sec> __device__ __forceinline__ void ring_loader(const Params& p, uint32_t sb_, int r_, int j_, int lane) {
    const uint32_t sb = opaque(sb_);
    const int r = opaque(r_), j = opaque(j_), nq = j >> 1, fs = 4 * (j & 1) + nq;
    const int fa = pass_f(fs, 0), fb = pass_f(fs, 1), fc = pass_f(fs, 2);
    const uint32_t* h2src = (const uint32_t*)__shfl_sync(~0u, (unsigned long long)(p.actb + (size_t)r * RB_WORDS + RB_H2), 0);
    const CUtensorMap* gmap = (const CUtensorMap*)__shfl_sync(~0u, (unsigned long long)(&p.ga + sec), 0);
#define BAR(i) (sb + M_BAR + 8 * (i))
#define kh (j & 1)
            int sl = 0;
#pragma unroll 1
            for (int s = 0; s < 28; s++) {
                if (s == 7) { wait_flags(g_flag + (8 * r + j) * 128 + 96 + lane, lds1(sb + M_EPOCH) + 1, 0xFFFFu); fence_async_global(); }
                const int ps = s < 14 ? 0 : s < 21 ? 1 : 2;
                const uint32_t half = ps < 2 ? 8192 : 4096;
                const int sp = sl;
                if (s >= PACE && s < PACE_END) mbar_wait(BAR(B_FULL + s - PACE), 0);
                mbar_wait(BAR(B_EMPTY + sp), (s >= 7 && s < 14) || s >= 21);
                expect_e(BAR(B_FULL + sp), half);
                tma3_e(sb + slot_off(sp) + sec * half, gmap + 2 * ps, 0, ps ? 64 * sl : 32 * s, ps == 0 ? fa >> 6 : ps == 1 ? fb >> 6 : fc >> 5, BAR(B_FULL + sp));
                sl = sl == 6 ? 0 : sl + 1;
            }
            if (!sec) PROFH(3);
#pragma unroll 1
            for (int e = 0; e < 4; e++) {
                const uint32_t dst = sb + slot_off(e) + sec * 8192, bar = BAR(B_FULL + e);
                const int f = (e < 2 ? fa + 64 * e : e == 2 ? fb : fc) + 32 * sec;
                mbar_wait(BAR(B_EMPTY + e), 0);
                expect_e(bar, e == 3 && sec ? 0 : 7168);
                if (!(e == 3 && sec)) { LOADW }
            }
            sl = 4;
            int e = 4;
#pragma unroll 1
            for (int grp = 0; grp < 9; grp++) {
                const int ps = grp >= 6 ? 2 : grp >= 3 ? 1 : 0;
                int sidx = grp - 3 * ps;
                if (sec && sidx == 0) { mbar_wait(BAR(B_HRDY + ps), 0); fence_async_global(); }
                sidx += sidx >= nq;
                int f = pass_f(4 * kh + sidx, ps);
#pragma unroll 1
                for (int k = 4 >> ps; k > 0; k--, e++, f += 32) {
                    const uint32_t dst = sb + slot_off(sl), bar = BAR(B_FULL + sl);
                    mbar_wait(BAR(B_EMPTY + sl), e >= 12 && e < 24);
                    if (e < WIN_END && e >= WIN) mbar_wait(BAR(B_FULL + (sl >= WIN ? sl - WIN : sl + 12 - WIN)), e - WIN >= 12);
                    expect_e(bar, sec ? 8192 : 7168);
                    if (!sec) { LOADW }
                    else bulk_e(dst + 8192, h2src + f * 64, 8192, bar);
                    sl = sl == 11 ? 0 : sl + 1;
                }
            }
            if (!sec) PROFH(4);
}

#define PROF_PARAMS
#define PROF_ARGS
__device__ __noinline__ void helper_late(const Params& p, int r_, int j_, int warp_ PROF_PARAMS) {
    extern __shared__ __align__(1024) unsigned char smem[];
    const uint32_t sb = (uint32_t)__cvta_generic_to_shared(smem);
    const int r = opaque(r_), j = opaque(j_), warp = opaque(warp_), nq = j >> 1, b = 8 * r + j;
    uint32_t* const act = (uint32_t*)__shfl_sync(~0u, (unsigned long long)(p.actb + (size_t)r * RB_WORDS), 0);
    {
        const int lane = fresh_tid() & 31;
        const uint32_t target = lds1(sb + M_EPOCH) + 1;
        if (warp == 8) { expect_e(BAR(B_XCH), 14336); expect_e(BAR(B_XCH + 1), 14336); }
            if (warp == 9) {
#pragma unroll 1
                for (int kv = 0; kv < 2; kv++) {
                    mbar_wait(BAR(B_PUB + kv), 0);
                    wait_flags(g_flag + b * 128 + lane, target, (r >= 2 ? 6u : r == 1 ? 2u : 0u) << (8 * kv));
                    fence_async_global();
                    const uint32_t dst = sb + OFF_Y + (kv ? Y_VR : Y_K);
                    expect_e(BAR(B_KRFULL + kv), r >= 2 ? 28672 : r == 1 ? 14336 : 0);
                    if (r >= 2) bulk_e(dst, act - 2 * RB_WORDS + RB_KV + j * 7168 + kv * 3584, 14336, BAR(B_KRFULL + kv));
                    if (r >= 1) bulk_e(dst + 14336, act - RB_WORDS + RB_KV + j * 7168 + kv * 3584, 14336, BAR(B_KRFULL + kv));
                    if (kv == 0) { PROFH(8); }
                }
            } else if (warp == 8) {
                uint4 v[8];
                mbar_wait(BAR(B_WOFULL), 0);
#pragma unroll
                for (int k = 0; k < 8; k++) v[k] = ld_relaxed4(mod_src(lane + 32 * k, r, j, true));
#pragma unroll
                for (int k = 0; k < 8; k++) mod_store(sb, v[k], mod_src(lane + 32 * k, r, j, true), lane + 32 * k);
                warp_arrive(BAR(B_MOD1));
            } else if (warp == 11) {
                if (kh == 1 && r < 14) {
                    const uint32_t wmbuf = sb + OFF_X + HALF;
                    const int mcol = 2 * DM + 32 * (4 * r + nq);
                    mbar_wait(BAR(B_XFREE), 0);
                    tma3_e(wmbuf, &p.wm2, mcol, 0, 0, BAR(B_WMFULL));
                    tma3_e(wmbuf + 14336, &p.wm2, mcol, 224, 0, BAR(B_WMFULL));
#pragma unroll 1
                    for (int wd = lane; wd < 224; wd += 32) {
                        const uint32_t cb = __ldg((const uint32_t*)p.c + wd);
                        sts1(wmbuf + 28672 + (wd >> 3) * 32 + (wd & 3) * 8 + (wd & 4), pack2(silu_bf(cb & 0xFFFFu), silu_bf(cb >> 16)));
                    }
                    __syncwarp();
                    mbar_wait(BAR(B_WMFULL), 0);
                    const uint32_t wa = wmbuf + (8 * (lane >> 4) + (lane & 7)) * 64 + ((lane >> 3) & 1) * 16;
                    float d[2][4] = {};
#pragma unroll 4
                    for (int ks = 0; ks < 28; ks++) {
                        uint32_t A[8];
                        ldsm4t(wa + ks * 1024, A); ldsm4t(wa + ks * 1024 + 32, A + 4);
                        const float2 v = lds2f(wmbuf + 28672 + ks * 32 + (lane & 3) * 8);
                        mma16816(d[0], A[0], A[1], A[2], A[3], __float_as_uint(v.x), __float_as_uint(v.y));
                        mma16816(d[1], A[4], A[5], A[6], A[7], __float_as_uint(v.x), __float_as_uint(v.y));
                    }
                    const int q = lane & 3, col = mcol + 8 * q + (lane >> 2);
                    const uint32_t word = mod_word(q == 0 ? d[0][0] : q == 1 ? d[0][2] : q == 2 ? d[1][0] : d[1][2], col, target);
#pragma unroll
                    for (int i = 0; i < 8; i++) st_relaxed(g_mod + i * 6 * DM + col, word);
                }
                warp_arrive(BAR(B_WMFREE));
                mbar_wait(BAR(B_VRFULL), 0);
                l2_prefetch_e((const char*)p.wg + (size_t)b * 12544, 12544);
                l2_prefetch_e((const char*)p.wu + (size_t)b * 12544, 12544);
#pragma unroll 1
                for (int k = 0; k < (r < 12 ? 2 : 1); k++) {
                    const int u = 28 * kh + r + 16 * k;
                    expect_e(BAR(B_XFULL + k), 7168);
                    tma3_e(sb + OFF_Y + 102400, &p.dn, 0, 32 * u, 7 * j, BAR(B_XFULL + k));
                    tma3_e(sb + OFF_Y + 102400 + 3584, &p.dn, 0, 32 * u, 7 * (j ^ 1), BAR(B_XFULL + k));
                    mbar_wait(BAR(B_XFULL + k), 1);
                    asm volatile("{\n.reg .pred p;\nelect.sync _|p, 0xffffffff;\n@p cp.async.bulk.global.shared::cta.bulk_group [%0], [%1], 7168;\n"
                                 "cp.async.bulk.commit_group;\ncp.async.bulk.wait_group 0;\n}" ::"l"(g_wd + (size_t)(u * 4 + nq) * 1792), "r"(sb + OFF_Y + 102400) : "memory");
                    __syncwarp();
                }
                warp_arrive(BAR(B_FULLK));
                fence_gpu();
                if (lane < 16) st_relaxed(g_flag + (8 * lane + j) * 128 + 96 + r, target);
            }
        if (warp == 8 || warp == 11) {
            const int sec = warp == 11;
            if (sec) ring_loader<1>(p, sb, r, j, lane); else ring_loader<0>(p, sb, r, j, lane);
            mbar_wait(BAR(B_DONE), 0);
        } else if (warp == 9) {
#pragma unroll
            for (int ev = 0; ev < 4; ev++) { expect_e(BAR(B_GFULL + ev), ev < 2 ? HALF / 2 : 16384 + 4096); expect_e(BAR(B_XFULL + 2 + ev), ev < 2 ? HALF / 2 : HALF - 16384); }
            mbar_wait(BAR(B_PUB + 2), 0);
            const uint32_t* fp = g_flag + b * 128 + 32 + lane;
            const int par = (target - 1) & 1;
#pragma unroll 1
            for (int n = 0, ev = 0; ev < 4; n++) {
                if (ev == 1) mbar_wait(BAR(B_PUB + 3), 0);
                uint32_t ok = __ballot_sync(~0u, (int)(ld_relaxed(fp) - target) >= 0) >> (8 * ev);
                while ((ok & 0xFFu) == 0xFFu) {
                    if (ev == 1) mbar_wait(BAR(B_FULLK), 1);
                    asm volatile("fence.acquire.gpu;" ::: "memory");
                    fence_async_global();
                    const int tile = (ev & 1) + (ev >> 1) * par * 2;
                    const uint32_t dst = sb + (ev == 0 ? OFF_X : OFF_Y + (ev & 1) * HALF), first = ev < 2 ? HALF / 2 : 16384;
                    const char* src = (const char*)(act + (ev == 1 && par ? RB_O2 : RB_O + ((ev >> 1) * 2 + tile) * 14336));
                    if (ev >= 2) bulk_e(sb + OFF_X + X_STAT + (ev & 1) * 49152, act + RB_ST + tile * 1024, 4096, BAR(B_GFULL + ev));
                    bulk_e(dst, src, first, BAR(B_GFULL + ev));
                    bulk_e(dst + first, src + first, HALF - first, BAR(B_XFULL + 2 + ev));
                    if (ev) PROFH(4 + ev);
                    ev++; ok >>= 8;
                }
                if (n > SPIN_LIMIT) __trap();
            }
            mbar_wait(BAR(B_XFULL + 5), 1);
#pragma unroll 1
            for (int hf = 0; hf < 3; hf++) {
                const int tile = (par ^ 1) * 2 + (hf & 1);
                uint4* xz = (uint4*)(act + (hf < 2 ? RB_X1 + tile * 14336 : par ? RB_O + 14336 : RB_O2) + j * 1792) + lane;
#pragma unroll
                for (int i = 0; i < 14; i++) xz[i * 32] = make_uint4(0, 0, 0, 0);
                ((uint4*)(act + RB_ST + (tile * 8 + j) * 128))[lane] = make_uint4(0, 0, 0, 0);
            }
#pragma unroll 1
            for (int ps = 0; ps < 3; ps++) {
                mbar_wait(BAR(B_PUB + 6 + ps), 0);
                wait_flags(g_flag + b * 128 + 64 + lane, target, (0x55u << kh) << (8 * ps));
                warp_arrive(BAR(B_HRDY + ps));
                PROFH(9 + ps);
            }
        } else {
#pragma unroll 1
            for (int k = 0; k < 9; k++) {
                uint32_t* fp = k < 2 ? g_flag + (b + 8 * lane) * 128 + k * 8 + lane : g_flag + (8 * r + lane) * 128 + 16 + k * 8 + j;
                mbar_wait(BAR(B_PUB + k), 0);
                if (k < 3 || k > 5) fence_gpu();
                if (k < 2 ? (lane == 1 || lane == 2) : lane < 8) st_relaxed(fp, target);
                if (k >= 3 && k <= 5) PROFH(k - 3);
            }
        }
    }
}

__global__ void __cluster_dims__(2, 1, 1) __launch_bounds__(384, 1) fused_block_kernel(const __grid_constant__ Params p) {
    extern __shared__ __align__(1024) unsigned char smem[];
    const uint32_t sb = (uint32_t)__cvta_generic_to_shared(smem);
    const int tid = threadIdx.x, lane = tid & 31, warp = __shfl_sync(~0u, tid >> 5, 0);
    const int m = blockIdx.x >> 1;
    int r, nq;
    if (m < 4) { r = 15; nq = m; }
    else if (m < 36) { r = (m - 4) & 7; nq = (m - 4) >> 3; }
    else { nq = (m - 36) / 7; r = m - 28 - 7 * nq; }
    const int j = opaque(2 * nq + (blockIdx.x & 1)), b = 8 * r + j, fs = 4 * kh + nq;
#define act (p.actb + (size_t)r * RB_WORDS)
    constexpr uint32_t sc = 0;
    if (lane == 0 && warp < 9 && warp != 6 && warp != 7) {
        const int i0 = warp == 8 ? 0 : 8 + 8 * warp, cnt = warp == 0 || warp == 8 ? 1 : warp < 3 ? 2 : 8;
#pragma unroll
        for (int k = 0; k < 8; k++) if (i0 + k != B_WMFULL) mbar_init(BAR(i0 + k), cnt);
        if (warp == 8) mbar_init(BAR(B_WMFULL), 1);
        asm volatile("fence.mbarrier_init.release.cluster;" ::: "memory");
        fence_async_smem();
    }

    if (warp >= 8) {
        const int lane = fresh_tid() & 31;
        const bool early = kh == 0, gemv = r < 14;
        const int mcol = early ? 16 * (4 * r + nq) : 2 * DM + 32 * (4 * r + nq);
        const uint32_t wmbuf = sb + OFF_Y + HALF;
        if (warp == 8) {
            __syncwarp();
            expect_e(BAR(B_WMFULL), gemv ? 28672 >> early : 0);
            if (early && gemv) { tma3_e(wmbuf, &p.wm, mcol, 0, 0, BAR(B_WMFULL)); tma3_e(wmbuf + 7168, &p.wm, mcol, 224, 0, BAR(B_WMFULL)); }
#pragma unroll
            for (int kb = 0; kb < XFIRST; kb++) {
                expect_e(BAR(B_XFULL + kb), 16384);
                tma3_e(sb + OFF_X + kb * 16384, &p.xm, 64 * kb, 128 * r, 0, BAR(B_XFULL + kb));
            }
        }
        asm volatile("setmaxnreg.dec.sync.aligned.u32 56;");
        if (warp == 9) {
#pragma unroll
            for (int i = 56; i < 64; i++) init_e(BAR(i), 1);
            fence_async_smem();
        }
        bar_arrive(0, 384);
        asm volatile("barrier.cluster.arrive.relaxed.aligned;" ::: "memory");
        if (warp == 8) {
#pragma unroll
            for (int kb = XFIRST; kb < 7; kb++) {
                expect_e(BAR(B_XFULL + kb), 16384);
                tma3_e(sb + OFF_X + kb * 16384, &p.xm, 64 * kb, 128 * r, 0, BAR(B_XFULL + kb));
            }
            if (KDELAY >= 0) { mbar_wait(BAR(B_XFULL + KDELAY), 0); l2_prefetch_e((const char*)p.wqkv + (size_t)b * 9408, 9408); }
#pragma unroll 1
            for (int mt = 0; mt < 4; mt++) {
                if (mt == 1) bar_sync(9, 384);
                if (mt == 3) mbar_wait(BAR(B_WMFREE), 0);
                if (mt) mbar_wait(BAR(mt == 1 ? B_MOD1 : mt == 2 ? B_XFREE : B_VRFULL), 0);
                const uint32_t bar = BAR(mt == 3 ? B_WOFULL : B_FULLK + mt), dst = sb + (mt < 2 ? OFF_Y : OFF_X) + (mt & 1) * HALF;
                const int c0 = (mt < 2 ? DM + DM * mt : 0) + 56 * j - 8 * kh;
                if (!sc) {
                    expect_e(bar, HALF);
                    tma3_e(dst, mt == 3 ? &p.wo : &p.qkv, c0, 0, 0, bar);
                    tma3_e(dst + HALF / 2, mt == 3 ? &p.wo : &p.qkv, c0, 224, 0, bar);
                }
            }
        } else {
            if (KDELAY < 0 && warp == 10) l2_prefetch_e((const char*)p.wqkv + (size_t)b * 9408, 9408);
            bar_sync(9, 384);
            if (sc) return;
            if (warp == 11 && early) {
                const uint32_t target = lds1(sb + M_EPOCH) + 1;
                mbar_wait(BAR(B_GEMV), 0);
                float sum = 0.f;
#pragma unroll
                for (int i = 0; i < 8; i++) sum += *(const float*)(smem + OFF_Y + HALF + 29696 + (i * 16 + (lane & 15)) * 4);
                uint32_t* mg = g_mod + mcol + (lane & 15) + (lane >> 4) * 4 * 6 * DM;
                const uint32_t word = mod_word(sum, mcol, target);
                if (gemv) { st_relaxed(mg, word); st_relaxed(mg + 6 * DM, word); st_relaxed(mg + 12 * DM, word); st_relaxed(mg + 18 * DM, word); }
            }
        }
    }
    if (LIKELY(warp < 8)) {
        const int w = warp >> 2, wi = warp & 3;
#define COORDS const int t = fresh_tid() & 127, lane = t & 31, q = lane & 3, lr = lane >> 2, ra = 64 * w + 16 * wi + lr; \
        const uint32_t lx = (lane >> 4) ^ (lane & 7), mrow = (64 * w + 16 * wi + ((lane >> 3) & 1) * 8 + (lane & 7)) * 128; \
        (void)q; (void)lr; (void)ra; (void)lx; (void)mrow;
        const int sid = 2 * (j & 3) + w;
#define RUN(k) (!sc || sid == (k))
#define WAIT(i, par) mbar_wait_c(BAR(i), (par) | sc)
        constexpr uint64_t DB128 = dconst(4096, 1024, 1);
        {
            const int wd = fresh_tid();
            const uint32_t cb = wd < 224 ? __ldg((const uint32_t*)p.c + wd) : 0u;
            if (wd == 255 && !sc) sts1(sb + M_EPOCH, atomicAdd(&g_ticket, 1u) / NCTA);
            sts1(sb + OFF_Y + HALF + 28672 + (wd >> 3) * 32 + (wd & 3) * 8 + (wd & 4), pack2(silu_bf(cb & 0xFFFFu), silu_bf(cb >> 16)));
        }
        bar_arrive(9, 384);
        bar_sync(0, 384);
        asm volatile("barrier.cluster.arrive.relaxed.aligned;" ::: "memory");
        asm volatile("setmaxnreg.inc.sync.aligned.u32 224;");
        PROFC(0);
        uint32_t xr[16];
        {
            COORDS
            uint32_t h[112];
            uint32_t ra2, na2, rb2, nb2;
            const int mi = min(128 * w + t, 223);
            const uint4* msrc = mod_src(mi, r, j, false);
            uint4 mv;
            {
                float ds[4] = {}, da[2][4] = {}, db[2][4] = {};
                const uint32_t ONE2 = 0x3F803F80u;
#pragma unroll
                for (int kb = 0; kb < 7; kb++) {
                    if (kb == GEMV_AT && kh == 0) { WAIT(B_WMFULL, 0); gemv_part(sb + OFF_Y + HALF, warp, lane); warp_arrive(BAR(B_GEMV)); }
                    WAIT(B_XFULL + kb, 0);
#pragma unroll
                    for (int k4 = 0; k4 < 4; k4++) ldsm4(sb + OFF_X + mrow + kb * 16384 + (((2 * k4) ^ lx) << 4), h + 16 * kb + 4 * k4);
#pragma unroll
                    for (int k4 = 0; k4 < 4; k4++) {
                        const uint32_t* f = h + 16 * kb + 4 * k4;
                        mma16816(ds, f[0], f[1], f[2], f[3], ONE2, ONE2);
                        mma1688(da[0], f[0], f[1], f[0]); mma1688(db[0], f[0], f[1], f[1]);
                        mma1688(da[1], f[2], f[3], f[2]); mma1688(db[1], f[2], f[3], f[3]);
                    }
                }
#pragma unroll
                for (int i = 0; i < 4; i++) {
                    const int ch = 7 * j + 2 * i + (lane >> 4);
                    ldsm4(sb + OFF_X + mrow + (ch >> 3) * 16384 + (((ch ^ lane) & 7) << 4), xr + 4 * i);
                }
                mv = ld_relaxed4(msrc);
                warp_arrive(BAR(B_XFREE));
                float qa = (lr & 1) ? da[0][1] + da[1][1] : da[0][0] + da[1][0];
                float qb = (lr & 1) ? db[0][3] + db[1][3] : db[0][2] + db[1][2];
                const int src = (lane & ~3) | (lr >> 1);
                qa = __shfl_sync(~0u, qa, src);
                qb = __shfl_sync(~0u, qb, src);
                ln_coeffs(ds[0] * (1.f / DM), qa * (1.f / DM), ra2, na2);
                ln_coeffs(ds[2] * (1.f / DM), qb * (1.f / DM), rb2, nb2);
#pragma unroll
                for (int i = 0; i < 4 * NPRE; i += 2) { h[i] = hfma2(h[i], ra2, na2); h[i + 1] = hfma2(h[i + 1], rb2, nb2); }
            }
            PROFC(1);
            {
                float ak[28], av[28], aq[28];
                uint32_t kp[14], vp[14];
                const uint64_t bq0 = (DB128 & ~0xFFFFFFFFull) | (mkdesc(sb + OFF_X, DB128) + kh), bk0 = bq0 + (OFF_Y >> 4), bv0 = bk0 + (HALF >> 4);
                uint32_t* kvg = act + RB_KV + j * 7168 + (8 * w + 2 * wi) * 224 + lane;
                mod_store(sb, mv, msrc, mi);
                bar_sync(3, 256);
                if (warp == 0) warp_arrive(BAR(B_MOD1));
                WAIT(B_FULLK, 0);
                PROFC(2);
                reg_def<28>(ak);
#pragma unroll
                for (int g4 = 0; g4 < 4; g4++) {
#pragma unroll
                    for (int ks = 7 * g4; ks < 7 * g4 + 7; ks++) {
                        const uint4 st = *(const uint4*)(smem + M_ST + ks * 64 + q * 16);
                        if (ks >= NPRE) {
                            h[4 * ks] = hfma2(h[4 * ks], ra2, na2); h[4 * ks + 1] = hfma2(h[4 * ks + 1], rb2, nb2);
                            h[4 * ks + 2] = hfma2(h[4 * ks + 2], ra2, na2); h[4 * ks + 3] = hfma2(h[4 * ks + 3], rb2, nb2);
                        }
                        h[4 * ks] = hfma2(h[4 * ks], st.x, st.y); h[4 * ks + 1] = hfma2(h[4 * ks + 1], st.x, st.y);
                        h[4 * ks + 2] = hfma2(h[4 * ks + 2], st.z, st.w); h[4 * ks + 3] = hfma2(h[4 * ks + 3], st.z, st.w);
                    }
                    WG_FENCE();
#pragma unroll
                    for (int ks = 7 * g4; ks < 7 * g4 + 7; ks++) wgmma_rl_56(ak, h[4 * ks], h[4 * ks + 1], h[4 * ks + 2], h[4 * ks + 3], bk0 + ks * 128, ks != 0);
                }
                WG_COMMIT();
                PROFC(3);
                reg_def<28>(av);
                WG_WAIT(0);
                reg_fence<28>(ak);
#pragma unroll
                for (int g = 0; g < 7; g++) {
                    kp[2 * g] = pack2(ak[4 * g], ak[4 * g + 1]); kp[2 * g + 1] = pack2(ak[4 * g + 2], ak[4 * g + 3]);
                    kvg[g * 32] = kp[2 * g]; kvg[224 + g * 32] = kp[2 * g + 1];
                }
                warp_arrive(BAR(B_PUB));
                PROFC(4);
                if (KEARLY) WAIT(B_FULLV, 0);
                WG_FENCE();
#pragma unroll
                for (int ks = KEARLY ? 0 : 8; ks < 28; ks++) wgmma_rl_56(av, h[4 * ks], h[4 * ks + 1], h[4 * ks + 2], h[4 * ks + 3], bv0 + ks * 128, ks != 0);
                WG_COMMIT();
                WAIT(B_FULLQ, 0);
                reg_def<28>(aq);
                WG_FENCE();
#pragma unroll
                for (int ks = 0; ks < 8; ks++) wgmma_rl_56(aq, h[4 * ks], h[4 * ks + 1], h[4 * ks + 2], h[4 * ks + 3], bq0 + ks * 128, ks != 0);
                WG_COMMIT();
                WG_WAIT(1);
                reg_fence<28>(av);
#pragma unroll
                for (int g = 0; g < 7; g++) {
                    vp[2 * g] = pack2(av[4 * g], av[4 * g + 1]); vp[2 * g + 1] = pack2(av[4 * g + 2], av[4 * g + 3]);
                    kvg[3584 + g * 32] = vp[2 * g]; kvg[3584 + 224 + g * 32] = vp[2 * g + 1];
                }
                warp_arrive(BAR(B_PUB + 1));
                PROFC(5);
                WG_FENCE();
#pragma unroll
                for (int ks = 8; ks < 28; ks++) wgmma_rl_56(aq, h[4 * ks], h[4 * ks + 1], h[4 * ks + 2], h[4 * ks + 3], bq0 + ks * 128, 1);
                WG_COMMIT();
                WAIT(B_PUB + 1, 0);
                const uint32_t rg = 8 * w + 2 * wi + ((lane >> 3) & 1);
                const uint32_t ko = sb + OFF_Y + Y_KOWN + rg * 896 + (lane & 7) * 16, qo = sb + OFF_Y + Y_Q + rg * 1024 + (lane >> 4) * 128 + (lane & 7) * 16;
#pragma unroll
                for (int g = 0; g < 6; g += 2) {
                    stsm4(ko + (g + (lane >> 4)) * 128, kp[2 * g], kp[2 * g + 1], kp[2 * g + 2], kp[2 * g + 3]);
                    stsm4(ko + (Y_VOWN - Y_KOWN) + (g + (lane >> 4)) * 128, vp[2 * g], vp[2 * g + 1], vp[2 * g + 2], vp[2 * g + 3]);
                }
                stsm4(ko + (lane >> 4) * (Y_VOWN - Y_KOWN) + 6 * 128, kp[12], kp[13], vp[12], vp[13]);
                WG_WAIT(0);
                reg_fence<28>(aq);
                __syncwarp();
                if (lane < 3 && w == 1) mbar_arrive(BAR(B_EMPTY + lane));
                uint32_t qp[14];
#pragma unroll
                for (int i = 0; i < 14; i++) qp[i] = pack2(aq[2 * i], aq[2 * i + 1]);
                stsm4(qo, qp[0], qp[1], qp[2], qp[3]);
                stsm4(qo + 256, qp[4], qp[5], q < 2 ? qp[6] : 0u, q < 2 ? qp[7] : 0u);
                stsm4(qo + 512, q < 2 ? 0u : qp[6], q < 2 ? 0u : qp[7], qp[8], qp[9]);
                stsm4(qo + 768, qp[10], qp[11], qp[12], qp[13]);
                if (!sc) bar_sync(3, 256);
            }
        }
        PROFC(6);
        WAIT(B_KRFULL, 0);
        if (ATT_OFF && w == ATT_WG) { const uint32_t t0 = clock(); while (clock() - t0 < ATT_OFF) {} }
        PROFC(7);
        if (RUN(2)) {
#pragma unroll 1
            for (int hf = sc; hf < 2; hf++) {
                COORDS
                float s[136];
                float na = 0.f, nb = 0.f;
                const float CS = 0.18898223650461361f * 1.4426950408889634f;
                const int kg0 = 8 * hf + 2 * wi;
                const int pmin = 16 - 8 * r - 4 * hf - wi;
                const float NEG = __int_as_float(0xFF800000);
                {
                    uint32_t F[8];
                    const uint32_t qa = sb + OFF_Y + Y_Q + (kg0 + ((lane >> 3) & 1)) * 1024 + (4 * w + (lane >> 4)) * 128 + (lane & 7) * 16;
                    ldsm4(qa, F); ldsm4(qa + 256, F + 4);
                    uint32_t ka = sb + OFF_Y + Y_K + kg0 * 896 + (3 * w + (lane >> 3)) * 128 + (lane & 7) * 16;
#pragma unroll
                    for (int g = 0; g < 34; g++) {
                        uint32_t B[4];
                        if (g >= 12 && g % 4 == 0) ka += __float_as_uint(s[4 * (g - 12)]) & p.zero;
                        ldsm4(ka + g * 896, B);
                        mma16816_first(s + 4 * g, F[0], F[1], F[2], F[3], B[0], B[1]);
                        mma16816_v(s + 4 * g, F[4], F[5], F[6], F[7], B[2], B[3]);
                    }
                    const bool c0 = 2 * q > lr, c1 = 2 * q + 1 > lr;
                    if (!c0) { s[0] = NEG; s[6] = NEG; }
                    if (!c1) { s[1] = NEG; s[7] = NEG; }
                    s[2] = NEG; s[3] = NEG;
                    if (c0) { s[128] = NEG; s[134] = NEG; }
                    if (c1) { s[129] = NEG; s[135] = NEG; }
                    s[132] = NEG; s[133] = NEG;
                    float ma = NEG, mb = NEG;
#pragma unroll
                    for (int pp = 0; pp < 17; pp++) {
                        const float* e = s + 8 * pp;
                        const float bias = pp < pmin ? NEG : 0.f;
                        ma = fmaxf(ma, fmaxf(fmaxf(e[0], e[1]), fmaxf(e[4], e[5])) + bias);
                        mb = fmaxf(mb, fmaxf(fmaxf(e[2], e[3]), fmaxf(e[6], e[7])) + bias);
                    }
                    ma = fmaxf(ma, __shfl_xor_sync(~0u, ma, 1)); mb = fmaxf(mb, __shfl_xor_sync(~0u, mb, 1));
                    ma = fmaxf(ma, __shfl_xor_sync(~0u, ma, 2)); mb = fmaxf(mb, __shfl_xor_sync(~0u, mb, 2));
                    na = -ma * CS; nb = -mb * CS;
                }
                PROFC(8 + 3 * hf);
                {
                    WAIT(B_VRFULL, 0);
                    float o[16] = {}, rs[4] = {};
                    uint32_t pk[2];
                    const uint32_t va = sb + OFF_Y + Y_VR + (kg0 + ((lane >> 3) & 1)) * 896 + (3 * w + (lane >> 4)) * 128 + (lane & 7) * 16;
#pragma unroll
                    for (int pp = 0; pp < 17; pp++) {
                        uint32_t B[8];
                        const uint32_t v = va + pp * 1792 + (pp == 16 || (pp >= 9 && kg0 + 2 * pp >= 32) ? Y_VOWN - 32 * 896 : 0);
                        ldsm4t(v, B); ldsm4t(v + 256, B + 4);
                        float e[8];
                        const float bias = __uint_as_float((pp < pmin ? 0xFF800000u : 0u) | ((pp < 2 ? B[0] : pk[pp & 1]) & p.zero));
#pragma unroll
                        for (int i = 0; i < 8; i++) e[i] = ex2(fmaf(s[8 * pp + i], CS, ((i & 2) ? nb : na) + bias));
                        const uint32_t p0 = pack2(e[0], e[1]), p1 = pack2(e[2], e[3]), p2 = pack2(e[4], e[5]), p3 = pack2(e[6], e[7]);
                        pk[pp & 1] = p3;
                        mma16816(rs, p0, p1, p2, p3, 0x3F803F80u, 0x3F803F80u);
#pragma unroll
                        for (int g = 0; g < 4; g++) mma16816(o + 4 * g, p0, p1, p2, p3, B[2 * g], B[2 * g + 1]);
                    }
                    PROFC(9 + 3 * hf);
                    const float ia = rcp(rs[0]), ib = rcp(rs[2]);
                    uint32_t* og = act + RB_O + hf * (14336 + (lds1(sb + M_EPOCH) & 1) * (RB_O2 - RB_O - 14336)) + (7 * j + 3 * w) * 256 + wi * 64 + lane;
#pragma unroll
                    for (int g = 0; g < 4; g++) {
                        if ((g == 3 - 3 * w) ? ((q >> 1) == w) : true) {
                            st_relaxed(og + g * 256, nz(pack2(o[4 * g] * ia, o[4 * g + 1] * ia)));
                            st_relaxed(og + g * 256 + 32, nz(pack2(o[4 * g + 2] * ib, o[4 * g + 3] * ib)));
                        }
                    }
                    warp_arrive(BAR(B_PUB + 2 + hf));
                    PROFC(10 + 3 * hf);
                }
            }
        }
        uint32_t x1p[14];
        COORDS
        constexpr uint64_t DT = dconst(1024, 128, 0);
        const int tile = opaque((lds1(sb + M_EPOCH) & 1) * 2 + w);
        if (RUN(4)) {
            float ac[28];
            const uint32_t ad = mkdesc(sb + (w ? OFF_Y + HALF : OFF_X), DT), bd = mkdesc(sb + OFF_X + HALF, DB128) + kh;
            WAIT(B_WOFULL, 0);
            WAIT(B_MOD1, 1);
            WAIT(B_GFULL + w, 0);
            PROFC(28);
            reg_def<28>(ac);
#pragma unroll 1
            for (int u = 0; u < 4; u++) {
                if (u == 2) WAIT(B_XFULL + 2 + w, 1);
                if (w == 1 && !(u & 1))
                    tile_check(act + ((tile >> 1) ? RB_O2 : RB_O + 14336) + u * 3584 + (lane >> 4) * 256 + wi * 64 + (lane & 15) * 4,
                               sb + OFF_Y + HALF + u * 14336 + (lane >> 4) * 1024 + wi * 256 + (lane & 15) * 16);
                WG_FENCE();
#pragma unroll
                for (int i = 0; i < 7; i++) wgmma_ss_56<DT, DB128>(ac, ad + (7 * u + i) * 128, bd + (7 * u + i) * 128, (u | i) != 0);
            }
            WG_COMMIT();
            WG_WAIT(0);
            reg_fence<28>(ac);
            PROFC(14);
            __syncwarp();
            if (lane < 3) mbar_arrive(BAR(B_EMPTY + 4 - w + lane));
            if (lane < 3 && w == 0) mbar_arrive(BAR(B_EMPTY + lane));
            float ds[4] = {}, da[4] = {}, db[4] = {};
            uint32_t* xo = act + RB_X1 + tile * 14336 + 7 * j * 256 + wi * 64 + lane;
#pragma unroll
            for (int g = 0; g < 7; g++) {
                const float2 ga = *(const float2*)(smem + M_G + (8 * g + 2 * q) * 4);
                x1p[2 * g] = pack2(fmaf(ga.x, ac[4 * g], bf_lo(xr[2 * g])), fmaf(ga.y, ac[4 * g + 1], bf_hi(xr[2 * g])));
                x1p[2 * g + 1] = pack2(fmaf(ga.x, ac[4 * g + 2], bf_lo(xr[2 * g + 1])), fmaf(ga.y, ac[4 * g + 3], bf_hi(xr[2 * g + 1])));
                st_relaxed(xo + g * 256, nz(x1p[2 * g])); st_relaxed(xo + g * 256 + 32, nz(x1p[2 * g + 1]));
                mma1688(ds, x1p[2 * g], x1p[2 * g + 1], 0x3F803F80u);
                mma1688(da, x1p[2 * g], x1p[2 * g + 1], x1p[2 * g]);
                mma1688(db, x1p[2 * g], x1p[2 * g + 1], x1p[2 * g + 1]);
            }
            const int src = (lane & ~3) | (lr >> 1);
            const float qa = __shfl_sync(~0u, (lr & 1) ? da[1] : da[0], src), qb = __shfl_sync(~0u, (lr & 1) ? db[3] : db[2], src);
            const float kk = (q & 1) ? ((q & 2) ? qb : qa) : ((q & 2) ? ds[2] : ds[0]);
            st_relaxed(act + RB_ST + ((tile * 8 + j) * 64 + 16 * wi + lr + 4 * (q & 2)) * 2 + (q & 1), nz(__float_as_uint(kk)));
            __syncwarp();
            if (lane < 2) mbar_arrive(BAR(B_PUB + 4 + w));
        } else reg_def<14>(x1p);
        PROFC(15);
        uint32_t h2a[32], h2b[24];
        {
            const int fa = pass_f(fs, 0), fb = pass_f(fs, 1), fc = pass_f(fs, 2);
            uint32_t* h2g = act + RB_H2 + (8 * w + 2 * wi) * 32 + lane;
            const uint32_t a0 = mkdesc(sb + OFF_Y + w * HALF, DT);
            if (RUN(3)) {
                uint32_t ra2, na2, rb2, nb2;
                {
                    const uint32_t* sg = act + RB_ST + ((tile * 8 + 2 * q) * 64 + 16 * wi + lr) * 2;
                    uint2 u[4];
                    WAIT(B_GFULL + 2 + w, 0);
                    PROFC(16);
#pragma unroll
                    for (int i = 0; i < 4; i++) { const float2 v = lds2f(sb + OFF_X + X_STAT + w * 49152 + ((2 * q + (i >> 1)) * 64 + 16 * wi + lr + 8 * (i & 1)) * 8); u[i] = make_uint2(__float_as_uint(v.x), __float_as_uint(v.y)); }
                    while (__any_sync(~0u, min(min(min(u[0].x, u[0].y), min(u[1].x, u[1].y)), min(min(u[2].x, u[2].y), min(u[3].x, u[3].y))) < 1u - sc)) {
#pragma unroll
                        for (int i = 0; i < 4; i++) u[i] = ld_relaxed2(sg + (i >> 1) * 128 + (i & 1) * 16);
                    }
                    warp_arrive(BAR(B_EMPTY + 3 + 3 * w));
                    float v[4] = {__uint_as_float(u[0].x) + __uint_as_float(u[2].x), __uint_as_float(u[0].y) + __uint_as_float(u[2].y),
                                  __uint_as_float(u[1].x) + __uint_as_float(u[3].x), __uint_as_float(u[1].y) + __uint_as_float(u[3].y)};
#pragma unroll
                    for (int i = 0; i < 4; i++) { v[i] += __shfl_xor_sync(~0u, v[i], 1); v[i] += __shfl_xor_sync(~0u, v[i], 2); }
                    ln_coeffs(v[0] * (1.f / DM), v[1] * (1.f / DM), ra2, na2);
                    ln_coeffs(v[2] * (1.f / DM), v[3] * (1.f / DM), rb2, nb2);
                }
                const uint32_t ha = sb + OFF_Y + w * HALF + (lane >> 4) * 1024 + (2 * wi + ((lane >> 3) & 1)) * 128 + (lane & 7) * 16;
                const uint32_t sta = sb + M_ST + q * 16;
                const uint32_t* xg = act + RB_X1 + tile * 14336 + (lane >> 4) * 256 + wi * 64 + (lane & 15) * 4;
                uint32_t x[8];
                const uint32_t xs = sb + OFF_Y + w * HALF + (lane >> 4) * 1024 + wi * 256 + (lane & 15) * 16;
                uint4 st[2];
                auto load = [&](int s) {
                    if (s == 4) mbar_wait_c(BAR(B_XFULL + 4 + w), 1);
                    ldsm4(ha + s * 4096, x); ldsm4(ha + s * 4096 + 2048, x + 4);
                    st[0] = lds4(sta + s * 128); st[1] = lds4(sta + s * 128 + 64);
                };
                auto prep = [&](int s, uint32_t* f) {
                    if (__any_sync(~0u, min(min(min(x[0], x[1]), min(x[2], x[3])), min(min(x[4], x[5]), min(x[6], x[7]))) < 1u - sc)) {
                        WG_WAIT(0);
                        x1_fix(xg, xs, s);
                        ldsm4(ha + s * 4096, x); ldsm4(ha + s * 4096 + 2048, x + 4);
                    }
#pragma unroll
                    for (int i = 0; i < 2; i++) {
                        f[4 * i] = hfma2(hfma2(x[4 * i], ra2, na2), st[i].x, st[i].y); f[4 * i + 1] = hfma2(hfma2(x[4 * i + 1], rb2, nb2), st[i].x, st[i].y);
                        f[4 * i + 2] = hfma2(hfma2(x[4 * i + 2], ra2, na2), st[i].z, st[i].w); f[4 * i + 3] = hfma2(hfma2(x[4 * i + 3], rb2, nb2), st[i].z, st[i].w);
                    }
                    if (s < 13) load(s + 1);
                    stsm4(ha + s * 4096, f[0], f[1], f[2], f[3]); stsm4(ha + s * 4096 + 2048, f[4], f[5], f[6], f[7]);
                };
                float ac[128];
                uint32_t fr[3][8];
                uint64_t bd = (DB128 & ~0xFFFFFFFFull) | mkdesc(sb, DB128);
                reg_def<128>(ac);
                load(0);
                prep(0, fr[0]);
                PROFC(17);
#pragma unroll
                for (int s = 0; s < 14; s++) {
                    const uint32_t* f = fr[s % 3];
                    WAIT(B_FULL + g1_slot(s), s >= 7);
                    WG_FENCE();
                    wgmma_rl_256(ac, f[0], f[1], f[2], f[3], bd, s != 0);
                    wgmma_rl_256(ac, f[4], f[5], f[6], f[7], bd + 128, 1);
                    bd += s == 6 ? p.zero - 6 * 1024ull : 1024;
                    WG_COMMIT();
                    if (s < 13) prep(s + 1, fr[(s + 1) % 3]);
                    if (s > 0) { WG_WAIT(1); warp_arrive(BAR(B_EMPTY + g1_slot(s - 1))); }
                }
                fence_async_smem();
                PROFC(18);
                WG_WAIT(0);
                reg_fence<128>(ac);
                warp_arrive(BAR(B_EMPTY + 6));
#pragma unroll
                for (int g = 0; g < 16; g++) {
                    h2a[2 * g] = hmul2(pack2_relu(ac[4 * g], ac[4 * g + 1]), pack2(ac[64 + 4 * g], ac[64 + 4 * g + 1]));
                    h2a[2 * g + 1] = hmul2(pack2_relu(ac[4 * g + 2], ac[4 * g + 3]), pack2(ac[64 + 4 * g + 2], ac[64 + 4 * g + 3]));
                }
                bar_sync(1 + w, 128);
            } else reg_def<32>(h2a);
            PROFC(19);
            if (RUN(5)) {
                float ac[64];
                reg_def<64>(ac);
                const uint32_t bx = mkdesc(sb, dconst(8192, 1024, 1));
#pragma unroll kB
                for (int s = 0; s < 7; s++) {
                    WAIT(B_FULL + s, 0);
                    const uint32_t ad = a0 + s * 512, bd = bx + (slot_off(s) >> 4);
                    WG_FENCE();
#pragma unroll
                    for (int k = 0; k < 4; k++) wgmma_ss_128<DT, DB128>(ac, ad + k * 128, bd + k * 128, (s | k) != 0);
                    WG_COMMIT();
                    if (s == 1) {
#pragma unroll
                        for (int g = 0; g < 16; g++) { h2g[(fa / 8 + g) * 512] = h2a[2 * g]; h2g[(fa / 8 + g) * 512 + 32] = h2a[2 * g + 1]; }
                        warp_arrive(BAR(B_PUB + 6));
                    }
                    if (s > 0) { WG_WAIT(1); warp_arrive(BAR(B_EMPTY + s - 1)); }
                }
                WG_WAIT(0);
                reg_fence<64>(ac);
                warp_arrive(BAR(B_EMPTY + 6));
#pragma unroll
                for (int g = 0; g < 8; g++) {
                    h2b[2 * g] = hmul2(pack2_relu(ac[4 * g], ac[4 * g + 1]), pack2(ac[32 + 4 * g], ac[32 + 4 * g + 1]));
                    h2b[2 * g + 1] = hmul2(pack2_relu(ac[4 * g + 2], ac[4 * g + 3]), pack2(ac[32 + 4 * g + 2], ac[32 + 4 * g + 3]));
                }
            } else reg_def<16>(h2b);
            PROFC(27);
            if (RUN(6)) {
                float ac[32];
                reg_def<32>(ac);
                const uint32_t bx = mkdesc(sb, dconst(4096, 512, 2));
#pragma unroll kC
                for (int s = 0; s < 7; s++) {
                    WAIT(B_FULL + s, 1);
                    const uint32_t ad = a0 + s * 512, bd = bx + (slot_off(s) >> 4);
                    WG_FENCE();
#pragma unroll
                    for (int k = 0; k < 4; k++) wgmma_ss_64<DT, dconst(4096, 512, 2)>(ac, ad + k * 128, bd + k * 64, (s | k) != 0);
                    WG_COMMIT();
                    if (s == 1) {
#pragma unroll
                        for (int g = 0; g < 8; g++) { h2g[(fb / 8 + g) * 512] = h2b[2 * g]; h2g[(fb / 8 + g) * 512 + 32] = h2b[2 * g + 1]; }
                        warp_arrive(BAR(B_PUB + 7));
                    }
                    if (s > 0) { WG_WAIT(1); warp_arrive(BAR(B_EMPTY + s - 1)); }
                }
                WG_WAIT(0);
                reg_fence<32>(ac);
                __syncwarp();
                if (lane < 6) mbar_arrive(BAR(B_EMPTY + 6 + lane));
                PROFC(20);
#pragma unroll
                for (int g = 0; g < 4; g++) {
                    h2b[16 + 2 * g] = hmul2(pack2_relu(ac[4 * g], ac[4 * g + 1]), pack2(ac[16 + 4 * g], ac[16 + 4 * g + 1]));
                    h2b[16 + 2 * g + 1] = hmul2(pack2_relu(ac[4 * g + 2], ac[4 * g + 3]), pack2(ac[16 + 4 * g + 2], ac[16 + 4 * g + 3]));
                    h2g[(fc / 8 + g) * 512] = h2b[16 + 2 * g]; h2g[(fc / 8 + g) * 512 + 32] = h2b[16 + 2 * g + 1];
                }
                warp_arrive(BAR(B_PUB + 8));
                asm volatile("barrier.cluster.wait.aligned;" ::: "memory");
                if (lane == 0 && !sc) {
                    uint32_t rb;
                    asm volatile("mapa.shared::cluster.u32 %0, %1, %2;" : "=r"(rb) : "r"(BAR(B_PEER)), "r"(kh ^ 1));
                    asm volatile("mbarrier.arrive.relaxed.cluster.shared::cluster.b64 _, [%0];" ::"r"(rb) : "memory");
                }
            } else reg_def<8>(h2b + 16);
        }
        PROFC(21);
        if (RUN(7)) {
            float ac[56];
            reg_def<56>(ac);
            constexpr uint64_t DAN = dconst(2048, 128, 0);
            constexpr uint64_t DW = dconst(128, 512, 0);
            const uint32_t bx = mkdesc(sb, DW);
#pragma unroll
            for (int e = 0; e < 4; e++) {
                WAIT(B_FULL + e, 0);
                const uint64_t bd = ((DW & ~0xFFFFFFFFull) | bx) + (slot_off(e) >> 4);
                const uint32_t* hh = e < 2 ? h2a + 16 * e : h2b + 16 * (e - 2);
                WG_FENCE();
#pragma unroll
                for (int k = 0; k < (e < 3 ? 4 : 2); k++) wgmma_rl_112(ac, hh[4 * k], hh[4 * k + 1], hh[4 * k + 2], hh[4 * k + 3], bd + (k >> 1) * 512 + (k & 1) * 16, (e | k) != 0);
                WG_COMMIT();
                if (e > 0) { WG_WAIT(1); warp_arrive(BAR(B_EMPTY + e - 1)); }
            }
            PROFC(22);
            uint32_t ad = mkdesc(sb + 4 * 16384 + 8192 + w * 1024, DAN), bd = bx + 4 * 1024, fb_ = BAR(B_FULL + 4), eb_ = BAR(B_EMPTY + 3), par = sc;
#pragma unroll 1
            for (int e = 4; e < 25; e++) {
                mbar_wait_c(fb_, par);
                WG_FENCE();
                wgmma_ss_112<DAN, DW>(ac, ad, bd, 1);
                wgmma_ss_112<DAN, DW>(ac, ad + 256, bd + 16, 1);
                WG_COMMIT();
                WG_WAIT(1);
                warp_arrive(eb_);
                eb_ = fb_ + 8 * (B_EMPTY - B_FULL);
                ad += 1024; bd += 1024; fb_ += 8;
                if (e == 11 || e == 23) { ad -= 12 * 1024; bd -= 12 * 1024; fb_ -= 96; par = (par ^ 1) | sc; }
            }
            mbar_wait_cluster(BAR(B_PEER), sc);
            WG_WAIT(0);
            reg_fence<56>(ac);
            PROFC(24);
            uint32_t rdst, rbar;
            asm volatile("mapa.shared::cluster.u32 %0, %1, %2;" : "=r"(rdst) : "r"(sb + OFF_Y + (5 + w) * 16384 + t * 16), "r"(kh ^ 1 ^ sc));
            asm volatile("mapa.shared::cluster.u32 %0, %1, %2;" : "=r"(rbar) : "r"(BAR(B_XCH + w)), "r"(kh ^ 1 ^ sc));
#pragma unroll
            for (int g = 0; g < 7; g++) {
                const float v0 = ac[28 + 4 * g + 0], v1 = ac[28 + 4 * g + 1];
                const float v2 = ac[28 + 4 * g + 2], v3 = ac[28 + 4 * g + 3];
                if (!sc) asm volatile("st.async.shared::cluster.mbarrier::complete_tx::bytes.v4.f32 [%0], {%1,%2,%3,%4}, [%5];"
                             ::"r"(rdst + g * 2048), "f"(v0), "f"(v1), "f"(v2), "f"(v3), "r"(rbar) : "memory");
            }
            mbar_wait_cluster(BAR(B_XCH + w), sc);
            PROFC(25);
            uint32_t op[16];
#pragma unroll
            for (int g = 0; g < 7; g++) {
                const uint4 rv = *(const uint4*)(smem + OFF_Y + (5 + w) * 16384 + t * 16 + g * 2048);
                const float2 gb = *(const float2*)(smem + M_G + 224 + (8 * g + 2 * q) * 4);
                const float v0 = ac[4 * g + 0] + __uint_as_float(rv.x), v1 = ac[4 * g + 1] + __uint_as_float(rv.y);
                const float v2 = ac[4 * g + 2] + __uint_as_float(rv.z), v3 = ac[4 * g + 3] + __uint_as_float(rv.w);
                op[2 * g] = pack2(fmaf(gb.x, v0, bf_lo(x1p[2 * g])), fmaf(gb.y, v1, bf_hi(x1p[2 * g])));
                op[2 * g + 1] = pack2(fmaf(gb.x, v2, bf_lo(x1p[2 * g + 1])), fmaf(gb.y, v3, bf_hi(x1p[2 * g + 1])));
            }
            WAIT(B_EMPTY + 1, 0);
            const uint32_t oc = sb + OUT_STAGE + warp * 1792;
            const uint32_t oa = oc + (((lane >> 3) & 1) * 8 + (lane & 7)) * 112 + (lane >> 4) * 16;
            stsm4(oa, op[0], op[1], op[2], op[3]); stsm4(oa + 32, op[4], op[5], op[6], op[7]); stsm4(oa + 64, op[8], op[9], op[10], op[11]);
            asm volatile("stmatrix.sync.aligned.m8n8.x2.shared.b16 [%0], {%1,%2};" ::"r"(oa + 96), "r"(op[12]), "r"(op[13]));
            fence_async_smem();
            __syncwarp();
            asm volatile("{\n.reg .pred p;\nelect.sync _|p, 0xffffffff;\n@p cp.async.bulk.tensor.3d.global.shared::cta.bulk_group [%0, {%2, %3, %4}], [%1];\n"
                         "cp.async.bulk.commit_group;\ncp.async.bulk.wait_group.read 0;\n}" ::"l"(&p.om), "r"(oc), "r"(56 * j), "r"(128 * r + 16 * warp), "r"(0) : "memory");
        }
        PROFC(26);
        bar_sync(1 + w, 128);
        if (wi == 0) warp_arrive(BAR(B_DONE));
        return;
    }
    helper_late(p, r, j, warp PROF_ARGS);
}

#undef act
typedef CUresult (*EncodeFn)(CUtensorMap*, CUtensorMapDataType, cuuint32_t, void*, const cuuint64_t*, const cuuint64_t*, const cuuint32_t*,
                             const cuuint32_t*, CUtensorMapInterleave, CUtensorMapSwizzle, CUtensorMapL2promotion, CUtensorMapFloatOOBfill);

static void make_map(EncodeFn fn, CUtensorMap* m, const void* ptr, uint64_t d0, uint64_t d1, uint64_t d2, uint64_t s1, uint64_t s2,
                     uint32_t b0, uint32_t b1, uint32_t b2, CUtensorMapSwizzle sw) {
    cuuint64_t dims[3] = {d0, d1, d2}, strides[2] = {s1, s2};
    cuuint32_t box[3] = {b0, b1, b2}, es[3] = {1, 1, 1};
    CUresult rc = fn(m, CU_TENSOR_MAP_DATA_TYPE_BFLOAT16, 3, (void*)ptr, dims, strides, box, es, CU_TENSOR_MAP_INTERLEAVE_NONE, sw,
                     CU_TENSOR_MAP_L2_PROMOTION_L2_128B, CU_TENSOR_MAP_FLOAT_OOB_FILL_NONE);
    (void)rc;
}

extern "C" void kernel_launch(void* const* d_in, const int* in_sizes, int n_in, void* d_out, int out_size) {
    (void)in_sizes; (void)n_in; (void)out_size;
    static EncodeFn fn = nullptr;
    static uint32_t* act_base = nullptr;
    if (!fn) {
        cudaDriverEntryPointQueryResult st;
        cudaGetDriverEntryPoint("cuTensorMapEncodeTiled", (void**)&fn, cudaEnableDefault, &st);
        void* a = nullptr;
        cudaGetSymbolAddress(&a, g_act);
        act_base = (uint32_t*)a;
        cudaFuncSetAttribute(fused_block_kernel, cudaFuncAttributeMaxDynamicSharedMemorySize, SMEM_BYTES);
    }
    Params p;
    p.x = (const bf16*)d_in[0];
    const bf16* wqkv = (const bf16*)d_in[1];
    p.wqkv = wqkv;
    p.wop = (const bf16*)d_in[2];
    p.wg = (const bf16*)d_in[4];
    p.wu = (const bf16*)d_in[5];
    p.wd = (const bf16*)d_in[6];
    p.c = (const bf16*)d_in[7];
    p.wmod = (const bf16*)d_in[8];
    p.out = (bf16*)d_out;
    p.zero = 0;
    p.actb = act_base;
    make_map(fn, &p.wm, p.wmod, 2688, 448, 1, 5376, 5376 * 448, 16, 224, 1, CU_TENSOR_MAP_SWIZZLE_NONE);
    make_map(fn, &p.wm2, p.wmod, 2688, 448, 1, 5376, 5376 * 448, 32, 224, 1, CU_TENSOR_MAP_SWIZZLE_NONE);
    make_map(fn, &p.om, p.out, 448, 2048, 1, 896, 896 * 2048, 56, 16, 1, CU_TENSOR_MAP_SWIZZLE_NONE);
    make_map(fn, &p.xm, p.x, 448, 2048, 1, 896, 896 * 2048, 64, 128, 1, CU_TENSOR_MAP_SWIZZLE_128B);
    make_map(fn, &p.qkv, wqkv, 1344, 448, 1, 2688, 2688 * 448, 64, 224, 1, CU_TENSOR_MAP_SWIZZLE_128B);
    make_map(fn, &p.wo, p.wop, 448, 448, 1, 896, 896 * 448, 64, 224, 1, CU_TENSOR_MAP_SWIZZLE_128B);
    make_map(fn, &p.ga, p.wg, 64, 448, 28, 3584, 128, 64, 32, 2, CU_TENSOR_MAP_SWIZZLE_128B);
    make_map(fn, &p.ua, p.wu, 64, 448, 28, 3584, 128, 64, 32, 2, CU_TENSOR_MAP_SWIZZLE_128B);
    make_map(fn, &p.gb, p.wg, 64, 448, 28, 3584, 128, 64, 64, 1, CU_TENSOR_MAP_SWIZZLE_128B);
    make_map(fn, &p.ub, p.wu, 64, 448, 28, 3584, 128, 64, 64, 1, CU_TENSOR_MAP_SWIZZLE_128B);
    make_map(fn, &p.gc, p.wg, 32, 448, 56, 3584, 64, 32, 64, 1, CU_TENSOR_MAP_SWIZZLE_64B);
    make_map(fn, &p.uc, p.wu, 32, 448, 56, 3584, 64, 32, 64, 1, CU_TENSOR_MAP_SWIZZLE_64B);
    make_map(fn, &p.dn, p.wd, 8, 1792, 56, 896, 16, 8, 32, 7, CU_TENSOR_MAP_SWIZZLE_NONE);
    fused_block_kernel<<<GRID, 384, SMEM_BYTES>>>(p);
}
```

```cpp
#include <cuda_runtime.h>
#include <cuda_bf16.h>
#include <cuda.h>
#include <stdint.h>

typedef __nv_bfloat16 bf16;

__device__ __forceinline__ void wgmma_rl_56(float* d, uint32_t a0, uint32_t a1, uint32_t a2, uint32_t a3, uint64_t db, int sd) {
  asm volatile("{\n.reg .pred p;\nsetp.ne.b32 p, %33, 0;\n"
    "wgmma.mma_async.sync.aligned.m64n56k16.f32.bf16.bf16 {%0,%1,%2,%3,%4,%5,%6,%7,%8,%9,%10,%11,%12,%13,%14,%15,%16,%17,%18,%19,%20,%21,%22,%23,%24,%25,%26,%27}, {%28,%29,%30,%31}, %32, p, 1, 1, 1;\n}\n"
    : "+f"(d[0]),"+f"(d[1]),"+f"(d[2]),"+f"(d[3]),"+f"(d[4]),"+f"(d[5]),"+f"(d[6]),"+f"(d[7]),"+f"(d[8]),"+f"(d[9]),"+f"(d[10]),"+f"(d[11]),"+f"(d[12]),"+f"(d[13]),"+f"(d[14]),"+f"(d[15]),"+f"(d[16]),"+f"(d[17]),"+f"(d[18]),"+f"(d[19]),"+f"(d[20]),"+f"(d[21]),"+f"(d[22]),"+f"(d[23]),"+f"(d[24]),"+f"(d[25]),"+f"(d[26]),"+f"(d[27])
    : "r"(a0), "r"(a1), "r"(a2), "r"(a3), "l"(db), "r"(sd));
}
template<uint64_t CA, uint64_t CB> __device__ __forceinline__ void wgmma_ss_56(float* d, uint32_t da, uint32_t db, int sd) {
  asm volatile("{\n.reg .pred p;\n.reg .b64 a, b;\nsetp.ne.b32 p, %30, 0;\nmov.b64 a, {%28, %31};\nmov.b64 b, {%29, %32};\n"
    "wgmma.mma_async.sync.aligned.m64n56k16.f32.bf16.bf16 {%0,%1,%2,%3,%4,%5,%6,%7,%8,%9,%10,%11,%12,%13,%14,%15,%16,%17,%18,%19,%20,%21,%22,%23,%24,%25,%26,%27}, a, b, p, 1, 1, 0, 1;\n}\n"
    : "+f"(d[0]),"+f"(d[1]),"+f"(d[2]),"+f"(d[3]),"+f"(d[4]),"+f"(d[5]),"+f"(d[6]),"+f"(d[7]),"+f"(d[8]),"+f"(d[9]),"+f"(d[10]),"+f"(d[11]),"+f"(d[12]),"+f"(d[13]),"+f"(d[14]),"+f"(d[15]),"+f"(d[16]),"+f"(d[17]),"+f"(d[18]),"+f"(d[19]),"+f"(d[20]),"+f"(d[21]),"+f"(d[22]),"+f"(d[23]),"+f"(d[24]),"+f"(d[25]),"+f"(d[26]),"+f"(d[27])
    : "r"(da), "r"(db), "r"(sd), "n"((uint32_t)(CA >> 32)), "n"((uint32_t)(CB >> 32)));
}
__device__ __forceinline__ void wgmma_rl_256(float* d, uint32_t a0, uint32_t a1, uint32_t a2, uint32_t a3, uint64_t db, int sd) {
  asm volatile("{\n.reg .pred p;\nsetp.ne.b32 p, %133, 0;\n"
    "wgmma.mma_async.sync.aligned.m64n256k16.f32.bf16.bf16 {%0,%1,%2,%3,%4,%5,%6,%7,%8,%9,%10,%11,%12,%13,%14,%15,%16,%17,%18,%19,%20,%21,%22,%23,%24,%25,%26,%27,%28,%29,%30,%31,%32,%33,%34,%35,%36,%37,%38,%39,%40,%41,%42,%43,%44,%45,%46,%47,%48,%49,%50,%51,%52,%53,%54,%55,%56,%57,%58,%59,%60,%61,%62,%63,%64,%65,%66,%67,%68,%69,%70,%71,%72,%73,%74,%75,%76,%77,%78,%79,%80,%81,%82,%83,%84,%85,%86,%87,%88,%89,%90,%91,%92,%93,%94,%95,%96,%97,%98,%99,%100,%101,%102,%103,%104,%105,%106,%107,%108,%109,%110,%111,%112,%113,%114,%115,%116,%117,%118,%119,%120,%121,%122,%123,%124,%125,%126,%127}, {%128,%129,%130,%131}, %132, p, 1, 1, 1;\n}\n"
    : "+f"(d[0]),"+f"(d[1]),"+f"(d[2]),"+f"(d[3]),"+f"(d[4]),"+f"(d[5]),"+f"(d[6]),"+f"(d[7]),"+f"(d[8]),"+f"(d[9]),"+f"(d[10]),"+f"(d[11]),"+f"(d[12]),"+f"(d[13]),"+f"(d[14]),"+f"(d[15]),"+f"(d[16]),"+f"(d[17]),"+f"(d[18]),"+f"(d[19]),"+f"(d[20]),"+f"(d[21]),"+f"(d[22]),"+f"(d[23]),"+f"(d[24]),"+f"(d[25]),"+f"(d[26]),"+f"(d[27]),"+f"(d[28]),"+f"(d[29]),"+f"(d[30]),"+f"(d[31]),"+f"(d[32]),"+f"(d[33]),"+f"(d[34]),"+f"(d[35]),"+f"(d[36]),"+f"(d[37]),"+f"(d[38]),"+f"(d[39]),"+f"(d[40]),"+f"(d[41]),"+f"(d[42]),"+f"(d[43]),"+f"(d[44]),"+f"(d[45]),"+f"(d[46]),"+f"(d[47]),"+f"(d[48]),"+f"(d[49]),"+f"(d[50]),"+f"(d[51]),"+f"(d[52]),"+f"(d[53]),"+f"(d[54]),"+f"(d[55]),"+f"(d[56]),"+f"(d[57]),"+f"(d[58]),"+f"(d[59]),"+f"(d[60]),"+f"(d[61]),"+f"(d[62]),"+f"(d[63]),"+f"(d[64]),"+f"(d[65]),"+f"(d[66]),"+f"(d[67]),"+f"(d[68]),"+f"(d[69]),"+f"(d[70]),"+f"(d[71]),"+f"(d[72]),"+f"(d[73]),"+f"(d[74]),"+f"(d[75]),"+f"(d[76]),"+f"(d[77]),"+f"(d[78]),"+f"(d[79]),"+f"(d[80]),"+f"(d[81]),"+f"(d[82]),"+f"(d[83]),"+f"(d[84]),"+f"(d[85]),"+f"(d[86]),"+f"(d[87]),"+f"(d[88]),"+f"(d[89]),"+f"(d[90]),"+f"(d[91]),"+f"(d[92]),"+f"(d[93]),"+f"(d[94]),"+f"(d[95]),"+f"(d[96]),"+f"(d[97]),"+f"(d[98]),"+f"(d[99]),"+f"(d[100]),"+f"(d[101]),"+f"(d[102]),"+f"(d[103]),"+f"(d[104]),"+f"(d[105]),"+f"(d[106]),"+f"(d[107]),"+f"(d[108]),"+f"(d[109]),"+f"(d[110]),"+f"(d[111]),"+f"(d[112]),"+f"(d[113]),"+f"(d[114]),"+f"(d[115]),"+f"(d[116]),"+f"(d[117]),"+f"(d[118]),"+f"(d[119]),"+f"(d[120]),"+f"(d[121]),"+f"(d[122]),"+f"(d[123]),"+f"(d[124]),"+f"(d[125]),"+f"(d[126]),"+f"(d[127])
    : "r"(a0), "r"(a1), "r"(a2), "r"(a3), "l"(db), "r"(sd));
}
template<uint64_t CA, uint64_t CB> __device__ __forceinline__ void wgmma_ss_128(float* d, uint32_t da, uint32_t db, int sd) {
  asm volatile("{\n.reg .pred p;\n.reg .b64 a, b;\nsetp.ne.b32 p, %66, 0;\nmov.b64 a, {%64, %67};\nmov.b64 b, {%65, %68};\n"
    "wgmma.mma_async.sync.aligned.m64n128k16.f32.bf16.bf16 {%0,%1,%2,%3,%4,%5,%6,%7,%8,%9,%10,%11,%12,%13,%14,%15,%16,%17,%18,%19,%20,%21,%22,%23,%24,%25,%26,%27,%28,%29,%30,%31,%32,%33,%34,%35,%36,%37,%38,%39,%40,%41,%42,%43,%44,%45,%46,%47,%48,%49,%50,%51,%52,%53,%54,%55,%56,%57,%58,%59,%60,%61,%62,%63}, a, b, p, 1, 1, 0, 1;\n}\n"
    : "+f"(d[0]),"+f"(d[1]),"+f"(d[2]),"+f"(d[3]),"+f"(d[4]),"+f"(d[5]),"+f"(d[6]),"+f"(d[7]),"+f"(d[8]),"+f"(d[9]),"+f"(d[10]),"+f"(d[11]),"+f"(d[12]),"+f"(d[13]),"+f"(d[14]),"+f"(d[15]),"+f"(d[16]),"+f"(d[17]),"+f"(d[18]),"+f"(d[19]),"+f"(d[20]),"+f"(d[21]),"+f"(d[22]),"+f"(d[23]),"+f"(d[24]),"+f"(d[25]),"+f"(d[26]),"+f"(d[27]),"+f"(d[28]),"+f"(d[29]),"+f"(d[30]),"+f"(d[31]),"+f"(d[32]),"+f"(d[33]),"+f"(d[34]),"+f"(d[35]),"+f"(d[36]),"+f"(d[37]),"+f"(d[38]),"+f"(d[39]),"+f"(d[40]),"+f"(d[41]),"+f"(d[42]),"+f"(d[43]),"+f"(d[44]),"+f"(d[45]),"+f"(d[46]),"+f"(d[47]),"+f"(d[48]),"+f"(d[49]),"+f"(d[50]),"+f"(d[51]),"+f"(d[52]),"+f"(d[53]),"+f"(d[54]),"+f"(d[55]),"+f"(d[56]),"+f"(d[57]),"+f"(d[58]),"+f"(d[59]),"+f"(d[60]),"+f"(d[61]),"+f"(d[62]),"+f"(d[63])
    : "r"(da), "r"(db), "r"(sd), "n"((uint32_t)(CA >> 32)), "n"((uint32_t)(CB >> 32)));
}
template<uint64_t CA, uint64_t CB> __device__ __forceinline__ void wgmma_ss_64(float* d, uint32_t da, uint32_t db, int sd) {
  asm volatile("{\n.reg .pred p;\n.reg .b64 a, b;\nsetp.ne.b32 p, %34, 0;\nmov.b64 a, {%32, %35};\nmov.b64 b, {%33, %36};\n"
    "wgmma.mma_async.sync.aligned.m64n64k16.f32.bf16.bf16 {%0,%1,%2,%3,%4,%5,%6,%7,%8,%9,%10,%11,%12,%13,%14,%15,%16,%17,%18,%19,%20,%21,%22,%23,%24,%25,%26,%27,%28,%29,%30,%31}, a, b, p, 1, 1, 0, 1;\n}\n"
    : "+f"(d[0]),"+f"(d[1]),"+f"(d[2]),"+f"(d[3]),"+f"(d[4]),"+f"(d[5]),"+f"(d[6]),"+f"(d[7]),"+f"(d[8]),"+f"(d[9]),"+f"(d[10]),"+f"(d[11]),"+f"(d[12]),"+f"(d[13]),"+f"(d[14]),"+f"(d[15]),"+f"(d[16]),"+f"(d[17]),"+f"(d[18]),"+f"(d[19]),"+f"(d[20]),"+f"(d[21]),"+f"(d[22]),"+f"(d[23]),"+f"(d[24]),"+f"(d[25]),"+f"(d[26]),"+f"(d[27]),"+f"(d[28]),"+f"(d[29]),"+f"(d[30]),"+f"(d[31])
    : "r"(da), "r"(db), "r"(sd), "n"((uint32_t)(CA >> 32)), "n"((uint32_t)(CB >> 32)));
}
template<uint64_t CA, uint64_t CB> __device__ __forceinline__ void wgmma_ss_112(float* d, uint32_t da, uint32_t db, int sd) {
  asm volatile("{\n.reg .pred p;\n.reg .b64 a, b;\nsetp.ne.b32 p, %58, 0;\nmov.b64 a, {%56, %59};\nmov.b64 b, {%57, %60};\n"
    "wgmma.mma_async.sync.aligned.m64n112k16.f32.bf16.bf16 {%0,%1,%2,%3,%4,%5,%6,%7,%8,%9,%10,%11,%12,%13,%14,%15,%16,%17,%18,%19,%20,%21,%22,%23,%24,%25,%26,%27,%28,%29,%30,%31,%32,%33,%34,%35,%36,%37,%38,%39,%40,%41,%42,%43,%44,%45,%46,%47,%48,%49,%50,%51,%52,%53,%54,%55}, a, b, p, 1, 1, 0, 1;\n}\n"
    : "+f"(d[0]),"+f"(d[1]),"+f"(d[2]),"+f"(d[3]),"+f"(d[4]),"+f"(d[5]),"+f"(d[6]),"+f"(d[7]),"+f"(d[8]),"+f"(d[9]),"+f"(d[10]),"+f"(d[11]),"+f"(d[12]),"+f"(d[13]),"+f"(d[14]),"+f"(d[15]),"+f"(d[16]),"+f"(d[17]),"+f"(d[18]),"+f"(d[19]),"+f"(d[20]),"+f"(d[21]),"+f"(d[22]),"+f"(d[23]),"+f"(d[24]),"+f"(d[25]),"+f"(d[26]),"+f"(d[27]),"+f"(d[28]),"+f"(d[29]),"+f"(d[30]),"+f"(d[31]),"+f"(d[32]),"+f"(d[33]),"+f"(d[34]),"+f"(d[35]),"+f"(d[36]),"+f"(d[37]),"+f"(d[38]),"+f"(d[39]),"+f"(d[40]),"+f"(d[41]),"+f"(d[42]),"+f"(d[43]),"+f"(d[44]),"+f"(d[45]),"+f"(d[46]),"+f"(d[47]),"+f"(d[48]),"+f"(d[49]),"+f"(d[50]),"+f"(d[51]),"+f"(d[52]),"+f"(d[53]),"+f"(d[54]),"+f"(d[55])
    : "r"(da), "r"(db), "r"(sd), "n"((uint32_t)(CA >> 32)), "n"((uint32_t)(CB >> 32)));
}
__device__ __forceinline__ void wgmma_rl_112(float* d, uint32_t a0, uint32_t a1, uint32_t a2, uint32_t a3, uint64_t db, int sd) {
  asm volatile("{\n.reg .pred p;\nsetp.ne.b32 p, %61, 0;\n"
    "wgmma.mma_async.sync.aligned.m64n112k16.f32.bf16.bf16 {%0,%1,%2,%3,%4,%5,%6,%7,%8,%9,%10,%11,%12,%13,%14,%15,%16,%17,%18,%19,%20,%21,%22,%23,%24,%25,%26,%27,%28,%29,%30,%31,%32,%33,%34,%35,%36,%37,%38,%39,%40,%41,%42,%43,%44,%45,%46,%47,%48,%49,%50,%51,%52,%53,%54,%55}, {%56,%57,%58,%59}, %60, p, 1, 1, 1;\n}\n"
    : "+f"(d[0]),"+f"(d[1]),"+f"(d[2]),"+f"(d[3]),"+f"(d[4]),"+f"(d[5]),"+f"(d[6]),"+f"(d[7]),"+f"(d[8]),"+f"(d[9]),"+f"(d[10]),"+f"(d[11]),"+f"(d[12]),"+f"(d[13]),"+f"(d[14]),"+f"(d[15]),"+f"(d[16]),"+f"(d[17]),"+f"(d[18]),"+f"(d[19]),"+f"(d[20]),"+f"(d[21]),"+f"(d[22]),"+f"(d[23]),"+f"(d[24]),"+f"(d[25]),"+f"(d[26]),"+f"(d[27]),"+f"(d[28]),"+f"(d[29]),"+f"(d[30]),"+f"(d[31]),"+f"(d[32]),"+f"(d[33]),"+f"(d[34]),"+f"(d[35]),"+f"(d[36]),"+f"(d[37]),"+f"(d[38]),"+f"(d[39]),"+f"(d[40]),"+f"(d[41]),"+f"(d[42]),"+f"(d[43]),"+f"(d[44]),"+f"(d[45]),"+f"(d[46]),"+f"(d[47]),"+f"(d[48]),"+f"(d[49]),"+f"(d[50]),"+f"(d[51]),"+f"(d[52]),"+f"(d[53]),"+f"(d[54]),"+f"(d[55])
    : "r"(a0), "r"(a1), "r"(a2), "r"(a3), "l"(db), "r"(sd));
}

constexpr int DM = 448;
constexpr int NCTA = 128;
#define MAPPING 1
#define GRID 128
#define PINGPONG 0
#define WIN 6
#define WIN_END 25
#define UNR_B 1
#define UNR_C 1
constexpr int kB = UNR_B, kC = UNR_C;
#define LIKELY(x) __builtin_expect(!!(x), 1)
#define PACE 1
#define PACE_END 6
#define GEMV_AT 1
#define NPRE 14
#define ATT_OFF 0
#define ATT_WG 1
#define XFIRST 7
#define KDELAY 0
#define KEARLY 1
#define MAP_S 4
constexpr int SPIN_LIMIT = 1 << 22;

constexpr uint32_t OFF_X = 0, OFF_Y = 114688, OFF_MISC = 229376, SMEM_BYTES = 232448;
constexpr uint32_t Y_VR = 0, Y_K = 28672, Y_KOWN = 57344, Y_VOWN = 71680, Y_Q = 86016;
constexpr uint32_t HALF = 57344;
constexpr uint32_t X_STAT = 49152;
constexpr uint32_t OUT_STAGE = 16384;
constexpr uint32_t M_BAR = OFF_MISC;
constexpr uint32_t M_ST = OFF_MISC + 512;
constexpr uint32_t M_G = OFF_MISC + 2304;
constexpr uint32_t M_EPOCH = OFF_MISC + 3040;
enum { B_XFULL = 0, B_FULLK = 7, B_FULLV = 8, B_FULLQ, B_KRFULL, B_VRFULL, B_WOFULL, B_XCH, B_MOD1 = 15, B_FULL = 16, B_WMFULL = 30,
       B_EMPTY = 32, B_XFREE = B_EMPTY + 12, B_GEMV, B_PEER,
       B_PUB = 47,
       B_WMFREE = 56, B_HRDY, B_GFULL = B_HRDY + 3, B_DONE = 31, B_DUMMY = B_GEMV };

__device__ uint32_t g_ticket;
__device__ __align__(128) uint32_t g_mod[8 * 6 * DM];
__device__ __align__(128) uint32_t g_flag[144 * 128];
constexpr int RB_WORDS = 262144, RB_KV = 0, RB_O = 57344, RB_X1 = 86016, RB_H2 = 143360, RB_ST = 258048;
__device__ __align__(128) uint32_t g_act[18 * RB_WORDS];
__device__ __align__(128) uint32_t g_wd[56 * 4 * 1792];
#define PROFH(id)
#define PROFH1(id)
#define PROFC(id)

struct alignas(64) Params {
    CUtensorMap wm, wm2, om, xm, qkv, wo, ga, ua, gb, ub, gc, uc, dn;
    const bf16 *x, *c, *wqkv, *wmod, *wg, *wu, *wd, *wop;
    bf16* out;
    uint32_t* actb;
    uint32_t zero;
};

__device__ __forceinline__ void mbar_init(uint32_t bar, int cnt) { asm volatile("mbarrier.init.shared::cta.b64 [%0], %1;" ::"r"(bar), "r"(cnt) : "memory"); }
__device__ __forceinline__ void mbar_expect_tx(uint32_t bar, uint32_t bytes) { asm volatile("mbarrier.arrive.expect_tx.shared::cta.b64 _, [%0], %1;" ::"r"(bar), "r"(bytes) : "memory"); }
__device__ __forceinline__ void mbar_arrive(uint32_t bar) { asm volatile("mbarrier.arrive.shared::cta.b64 _, [%0];" ::"r"(bar) : "memory"); }
__device__ __forceinline__ void mbar_wait(uint32_t bar, uint32_t parity) {
    uint32_t ok; int n = 0;
    do {
        asm volatile("{\n.reg .pred p;\nmbarrier.try_wait.parity.shared::cta.b64 p, [%1], %2;\nselp.u32 %0, 1, 0, p;\n}" : "=r"(ok) : "r"(bar), "r"(parity) : "memory");
        if (++n > SPIN_LIMIT) __trap();
    } while (!ok);
}
__device__ __forceinline__ void mbar_wait_c(uint32_t bar, uint32_t parity) {
    asm volatile("{\n.reg .pred p;\nWL:\nmbarrier.try_wait.parity.shared::cta.b64 p, [%0], %1, 0x989680;\n@!p bra WL;\n}" ::"r"(bar), "r"(parity) : "memory");
}
__device__ __forceinline__ void mbar_wait_cluster(uint32_t bar, uint32_t parity) {
    asm volatile("{\n.reg .pred p;\nWL:\nmbarrier.try_wait.parity.acquire.cluster.shared::cta.b64 p, [%0], %1, 0x989680;\n@!p bra WL;\n}" ::"r"(bar), "r"(parity) : "memory");
}
__device__ __forceinline__ void warp_arrive(uint32_t bar) {
    __syncwarp();
    asm volatile("{\n.reg .pred p;\nelect.sync _|p, 0xffffffff;\n@p mbarrier.arrive.shared::cta.b64 _, [%0];\n}" ::"r"(bar) : "memory");
}
__device__ __forceinline__ int opaque(int v) { return __shfl_sync(~0u, v, 0); }
__device__ __forceinline__ int fresh_tid() { int v; asm volatile("mov.u32 %0, %%tid.x;" : "=r"(v)); return v; }
__device__ __forceinline__ void bar_sync(int id, int n) { asm volatile("bar.sync %0, %1;" ::"r"(id), "r"(n) : "memory"); }
__device__ __forceinline__ void bar_arrive(int id, int n) { asm volatile("bar.arrive %0, %1;" ::"r"(id), "r"(n) : "memory"); }
__device__ __forceinline__ void fence_async_smem() { asm volatile("fence.proxy.async.shared::cta;" ::: "memory"); }
__device__ __forceinline__ void fence_async_global() { asm volatile("fence.proxy.async.global;" ::: "memory"); }
__device__ __forceinline__ void fence_gpu() { asm volatile("fence.release.gpu;" ::: "memory"); }
__device__ __forceinline__ void tma3(uint32_t dst, const CUtensorMap* m, int c0, int c1, int c2, uint32_t bar) {
    asm volatile("cp.async.bulk.tensor.3d.shared::cluster.global.mbarrier::complete_tx::bytes [%0], [%1, {%3, %4, %5}], [%2];"
                 ::"r"(dst), "l"(m), "r"(bar), "r"(c0), "r"(c1), "r"(c2) : "memory");
}
__device__ __forceinline__ void bulk_load(uint32_t dst, const void* src, uint32_t bytes, uint32_t bar) {
    asm volatile("cp.async.bulk.shared::cluster.global.mbarrier::complete_tx::bytes [%0], [%1], %2, [%3];" ::"r"(dst), "l"(src), "r"(bytes), "r"(bar) : "memory");
}
__device__ __forceinline__ void expect_e(uint32_t bar, uint32_t bytes) {
    asm volatile("{\n.reg .pred p;\nelect.sync _|p, 0xffffffff;\n@p mbarrier.arrive.expect_tx.shared::cta.b64 _, [%0], %1;\n}" ::"r"(bar), "r"(bytes) : "memory");
}
__device__ __forceinline__ void tma3_e(uint32_t dst, const CUtensorMap* m, int c0, int c1, int c2, uint32_t bar) {
    asm volatile("{\n.reg .pred p;\nelect.sync _|p, 0xffffffff;\n@p cp.async.bulk.tensor.3d.shared::cluster.global.mbarrier::complete_tx::bytes [%0], [%1, {%3, %4, %5}], [%2];\n}"
                 ::"r"(dst), "l"(m), "r"(bar), "r"(c0), "r"(c1), "r"(c2) : "memory");
}
__device__ __forceinline__ void bulk_e(uint32_t dst, const void* src, uint32_t bytes, uint32_t bar) {
    asm volatile("{\n.reg .pred p;\nelect.sync _|p, 0xffffffff;\n@p cp.async.bulk.shared::cluster.global.mbarrier::complete_tx::bytes [%0], [%1], %2, [%3];\n}"
                 ::"r"(dst), "l"(src), "r"(bytes), "r"(bar) : "memory");
}
__device__ __forceinline__ void init_e(uint32_t bar, int cnt) {
    asm volatile("{\n.reg .pred p;\nelect.sync _|p, 0xffffffff;\n@p mbarrier.init.shared::cta.b64 [%0], %1;\n}" ::"r"(bar), "r"(cnt) : "memory");
}
__device__ __forceinline__ void l2_prefetch_e(const void* src, uint32_t bytes) {
    asm volatile("{\n.reg .pred p;\nelect.sync _|p, 0xffffffff;\n@p cp.async.bulk.prefetch.L2.global [%0], %1;\n}" ::"l"(src), "r"(bytes) : "memory");
}
__device__ __forceinline__ uint32_t ld_relaxed(const uint32_t* p) { uint32_t v; asm volatile("ld.relaxed.gpu.global.u32 %0, [%1];" : "=r"(v) : "l"(p) : "memory"); return v; }
__device__ __forceinline__ void st_relaxed(uint32_t* p, uint32_t v) { asm volatile("st.relaxed.gpu.global.u32 [%0], %1;" ::"l"(p), "r"(v) : "memory"); }
__device__ __forceinline__ uint4 ld_relaxed4(const uint4* p) { uint4 v; asm volatile("ld.relaxed.gpu.global.v4.u32 {%0,%1,%2,%3}, [%4];" : "=r"(v.x), "=r"(v.y), "=r"(v.z), "=r"(v.w) : "l"(p) : "memory"); return v; }
__device__ __forceinline__ void st_relaxed4(uint4* p, uint4 v) { asm volatile("st.relaxed.gpu.global.v4.u32 [%0], {%1,%2,%3,%4};" ::"l"(p), "r"(v.x), "r"(v.y), "r"(v.z), "r"(v.w) : "memory"); }
__device__ __forceinline__ uint4 ldg_nc4(const void* p) { uint4 v; asm volatile("ld.global.nc.L1::no_allocate.v4.u32 {%0,%1,%2,%3}, [%4];" : "=r"(v.x), "=r"(v.y), "=r"(v.z), "=r"(v.w) : "l"(p)); return v; }
__device__ __forceinline__ uint32_t ldg_nc(const void* p) { uint32_t v; asm volatile("ld.global.nc.u32 %0, [%1];" : "=r"(v) : "l"(p)); return v; }
__device__ __forceinline__ uint32_t ld_acquire(const uint32_t* p) { uint32_t v; asm volatile("ld.acquire.gpu.global.u32 %0, [%1];" : "=r"(v) : "l"(p) : "memory"); return v; }
__device__ __forceinline__ uint4 lds4(uint32_t a) { uint4 v; asm volatile("ld.shared.v4.u32 {%0,%1,%2,%3}, [%4];" : "=r"(v.x), "=r"(v.y), "=r"(v.z), "=r"(v.w) : "r"(a) : "memory"); return v; }
__device__ __forceinline__ float2 lds2f(uint32_t a) { float2 v; asm volatile("ld.shared.v2.f32 {%0,%1}, [%2];" : "=f"(v.x), "=f"(v.y) : "r"(a) : "memory"); return v; }
__device__ __forceinline__ uint32_t lds1(uint32_t a) { uint32_t v; asm volatile("ld.shared.u32 %0, [%1];" : "=r"(v) : "r"(a) : "memory"); return v; }
__device__ __forceinline__ void sts4(uint32_t a, uint4 v) { asm volatile("st.shared.v4.u32 [%0], {%1,%2,%3,%4};" ::"r"(a), "r"(v.x), "r"(v.y), "r"(v.z), "r"(v.w) : "memory"); }
__device__ __forceinline__ void sts2(uint32_t a, uint32_t x, uint32_t y) { asm volatile("st.shared.v2.u32 [%0], {%1,%2};" ::"r"(a), "r"(x), "r"(y) : "memory"); }
__device__ __forceinline__ void sts1(uint32_t a, uint32_t v) { asm volatile("st.shared.u32 [%0], %1;" ::"r"(a), "r"(v) : "memory"); }
__device__ __forceinline__ void stsm4(uint32_t a, uint32_t r0, uint32_t r1, uint32_t r2, uint32_t r3) {
    asm volatile("stmatrix.sync.aligned.m8n8.x4.shared.b16 [%0], {%1,%2,%3,%4};" ::"r"(a), "r"(r0), "r"(r1), "r"(r2), "r"(r3));
}
__device__ __forceinline__ uint32_t pack2(float lo, float hi) { uint32_t r; asm("cvt.rn.bf16x2.f32 %0, %1, %2;" : "=r"(r) : "f"(hi), "f"(lo)); return r; }
__device__ __forceinline__ uint32_t pack2_relu(float lo, float hi) { uint32_t r; asm("cvt.rn.relu.bf16x2.f32 %0, %1, %2;" : "=r"(r) : "f"(hi), "f"(lo)); return r; }
__device__ __forceinline__ uint32_t hfma2(uint32_t a, uint32_t b, uint32_t c) { uint32_t r; asm("fma.rn.bf16x2 %0, %1, %2, %3;" : "=r"(r) : "r"(a), "r"(b), "r"(c)); return r; }
__device__ __forceinline__ uint32_t hmul2(uint32_t a, uint32_t b) { uint32_t r; asm("mul.rn.bf16x2 %0, %1, %2;" : "=r"(r) : "r"(a), "r"(b)); return r; }
__device__ __forceinline__ float bf_lo(uint32_t v) { return __uint_as_float(v << 16); }
__device__ __forceinline__ float bf_hi(uint32_t v) { return __uint_as_float(v & 0xFFFF0000u); }
__device__ __forceinline__ float bf_round(float v) { return bf_lo(pack2(v, 0.f)); }
__device__ __forceinline__ float ex2(float x) { float r; asm("ex2.approx.ftz.f32 %0, %1;" : "=f"(r) : "f"(x)); return r; }
__device__ __forceinline__ void mma16816(float* d, uint32_t a0, uint32_t a1, uint32_t a2, uint32_t a3, uint32_t b0, uint32_t b1) {
    asm("mma.sync.aligned.m16n8k16.row.col.f32.bf16.bf16.f32 {%0,%1,%2,%3}, {%4,%5,%6,%7}, {%8,%9}, {%0,%1,%2,%3};"
        : "+f"(d[0]), "+f"(d[1]), "+f"(d[2]), "+f"(d[3]) : "r"(a0), "r"(a1), "r"(a2), "r"(a3), "r"(b0), "r"(b1));
}
__device__ __forceinline__ void mma16816_first(float* d, uint32_t a0, uint32_t a1, uint32_t a2, uint32_t a3, uint32_t b0, uint32_t b1) {
    asm volatile("mma.sync.aligned.m16n8k16.row.col.f32.bf16.bf16.f32 {%0,%1,%2,%3}, {%4,%5,%6,%7}, {%8,%9}, {%10,%10,%10,%10};"
        : "=f"(d[0]), "=f"(d[1]), "=f"(d[2]), "=f"(d[3]) : "r"(a0), "r"(a1), "r"(a2), "r"(a3), "r"(b0), "r"(b1), "f"(0.f));
}
__device__ __forceinline__ void mma16816_v(float* d, uint32_t a0, uint32_t a1, uint32_t a2, uint32_t a3, uint32_t b0, uint32_t b1) {
    asm volatile("mma.sync.aligned.m16n8k16.row.col.f32.bf16.bf16.f32 {%0,%1,%2,%3}, {%4,%5,%6,%7}, {%8,%9}, {%0,%1,%2,%3};"
        : "+f"(d[0]), "+f"(d[1]), "+f"(d[2]), "+f"(d[3]) : "r"(a0), "r"(a1), "r"(a2), "r"(a3), "r"(b0), "r"(b1));
}
__device__ __forceinline__ void mma1688(float* d, uint32_t a0, uint32_t a1, uint32_t b0) {
    asm("mma.sync.aligned.m16n8k8.row.col.f32.bf16.bf16.f32 {%0,%1,%2,%3}, {%4,%5}, {%6}, {%0,%1,%2,%3};"
        : "+f"(d[0]), "+f"(d[1]), "+f"(d[2]), "+f"(d[3]) : "r"(a0), "r"(a1), "r"(b0));
}
__device__ __forceinline__ void ldsm4(uint32_t a, uint32_t* r) {
    asm volatile("ldmatrix.sync.aligned.m8n8.x4.shared.b16 {%0,%1,%2,%3}, [%4];" : "=r"(r[0]), "=r"(r[1]), "=r"(r[2]), "=r"(r[3]) : "r"(a));
}
__device__ __forceinline__ void ldsm4t(uint32_t a, uint32_t* r) {
    asm volatile("ldmatrix.sync.aligned.m8n8.x4.trans.shared.b16 {%0,%1,%2,%3}, [%4];" : "=r"(r[0]), "=r"(r[1]), "=r"(r[2]), "=r"(r[3]) : "r"(a));
}
__device__ __forceinline__ uint32_t nz(uint32_t v) { uint32_t r; asm("max.u32 %0, %1, 1;" : "=r"(r) : "r"(v)); return r; }
__device__ __forceinline__ float rcp(float x) { float r; asm("rcp.approx.ftz.f32 %0, %1;" : "=f"(r) : "f"(x)); return r; }
__device__ __forceinline__ uint2 ld_relaxed2(const void* p) { uint2 v; asm volatile("ld.relaxed.gpu.global.v2.u32 {%0,%1}, [%2];" : "=r"(v.x), "=r"(v.y) : "l"(p) : "memory"); return v; }
__device__ __forceinline__ void st_relaxed2(void* p, uint32_t x, uint32_t y) { asm volatile("st.relaxed.gpu.global.v2.u32 [%0], {%1,%2};" ::"l"(p), "r"(max(x, 1u)), "r"(max(y, 1u)) : "memory"); }
__host__ __device__ constexpr uint64_t dconst(uint32_t lbo, uint32_t sbo, uint32_t swz) {
    return ((uint64_t)(lbo >> 4) << 16) | ((uint64_t)(sbo >> 4) << 32) | ((uint64_t)swz << 62);
}
__device__ __forceinline__ uint32_t mkdesc(uint32_t addr, uint64_t c) { return (uint32_t)c | ((addr & 0x3FFFF) >> 4); }
#define WG_FENCE() asm volatile("wgmma.fence.sync.aligned;" ::: "memory")
#define WG_COMMIT() asm volatile("wgmma.commit_group.sync.aligned;" ::: "memory")
#define WG_WAIT(n) asm volatile("wgmma.wait_group.sync.aligned %0;" ::"n"(n) : "memory")
template <int N> __device__ __forceinline__ void reg_fence(float* d) {
#pragma unroll
    for (int i = 0; i < N; i++) asm volatile("" : "+f"(d[i])::"memory");
}
template <int N> __device__ __forceinline__ void reg_def(float* d) {
#pragma unroll
    for (int i = 0; i < N; i++) asm volatile("" : "=f"(d[i]));
}
template <int N> __device__ __forceinline__ void reg_def(uint32_t* d) {
#pragma unroll
    for (int i = 0; i < N; i++) asm volatile("" : "=r"(d[i]));
}
__device__ __forceinline__ bool is_unset(uint4 v) { return min(min(v.x, v.y), min(v.z, v.w)) == 0u; }
__device__ __forceinline__ uint4 nz4(uint32_t a, uint32_t b, uint32_t c, uint32_t d) { return make_uint4(max(a, 1u), max(b, 1u), max(c, 1u), max(d, 1u)); }
__device__ __forceinline__ void wait_flags(const uint32_t* p, uint32_t target, uint32_t mask) {
    int n = 0;
    while (~__ballot_sync(~0u, (int)(ld_relaxed(p) - target) >= 0) & mask) { if (++n > SPIN_LIMIT) __trap(); }
    asm volatile("fence.acquire.gpu;" ::: "memory");
}
__device__ __forceinline__ float silu_bf(uint32_t cbits) {
    const float c = __uint_as_float(cbits << 16);
    return bf_round(__fdividef(c, 1.f + fminf(ex2(-1.4426950408889634f * c), 1e30f)));
}
__device__ __forceinline__ void gemv_part(uint32_t wmbuf, int wp, int lane) {
    const uint32_t wa = wmbuf + wp * 512 + (8 * (lane >> 4) + (lane & 7)) * 32 + ((lane >> 3) & 1) * 16;
    float d[4] = {};
#pragma unroll
    for (int i = 0; i < 4; i++) {
        uint32_t A[4];
        const float2 v = lds2f(wmbuf + 28672 + (wp + 8 * i) * 32 + (lane & 3) * 8);
        ldsm4t(wa + (i < 3 || wp < 4 ? i : 0) * 4096, A);
        mma16816(d, A[0], A[1], A[2], A[3], __float_as_uint(v.x), __float_as_uint(v.y));
    }
    if ((lane & 3) == 0) {
        sts1(wmbuf + 29696 + (wp * 16 + (lane >> 2)) * 4, __float_as_uint(d[0]));
        sts1(wmbuf + 29696 + (wp * 16 + 8 + (lane >> 2)) * 4, __float_as_uint(d[2]));
    }
}
__device__ __forceinline__ uint32_t mod_word(float v, int col, uint32_t target) {
    v = bf_round(v);
    if ((col >= DM && col < 2 * DM) || (col >= 4 * DM && col < 5 * DM)) v += 1.f;
    return (pack2(v, 0.f) << 16) | (target & 0xFFFFu);
}
__device__ __forceinline__ const uint4* mod_src(int i, int r, int j, bool p2) {
    i = min(i, p2 ? 251 : 223);
    return (const uint4*)g_mod + (r & 7) * (6 * DM / 4) + (i < 224 ? (p2 ? 336 : 0) + i : (i < 238 ? 14 * j + i : 14 * j + i + 322));
}
__device__ __forceinline__ void mod_store(uint32_t sb, uint4 v, const uint4* src, int i) {
    const uint32_t tag = lds1(sb + M_EPOCH) + 1;
    while (__any_sync(~0u, (((v.x ^ tag) | (v.y ^ tag) | (v.z ^ tag) | (v.w ^ tag)) & 0xFFFFu) != 0u)) v = ld_relaxed4(src);
    if (i < 224) {
        const int isc = i >= 112, c4 = i - 112 * isc;
        const uint32_t a = sb + M_ST + (c4 >> 2) * 64 + (c4 & 1) * 32 + (c4 & 2) * 4 + (isc ? 0 : 4);
        sts1(a, __byte_perm(v.x, v.y, 0x7632));
        sts1(a + 16, __byte_perm(v.z, v.w, 0x7632));
    } else if (i < 252) {
        sts4(sb + M_G + (i - 224) * 16, make_uint4(v.x & 0xFFFF0000u, v.y & 0xFFFF0000u, v.z & 0xFFFF0000u, v.w & 0xFFFF0000u));
    }
}
__device__ __forceinline__ int pass_f(int fs, int ps) { return 224 * fs + ((fs & 1) ? (ps == 0 ? 96 : ps == 1 ? 32 : 0) : (ps == 0 ? 0 : ps == 1 ? 128 : 192)); }
__device__ __forceinline__ constexpr uint32_t slot_off(int l) { return l * 16384; }
__device__ __forceinline__ constexpr int g1_slot(int s) { return s % 7; }
__device__ __noinline__ void x1_fix(const uint32_t* g, uint32_t sa, int s) {
#pragma unroll 1
    for (int k = 4 * s; k < 4 * s + 4;) {
        const uint4 v = ld_relaxed4((const uint4*)(g + k * 256));
        sts4(sa + k * 1024, v);
        k += 2 * __all_sync(~0u, min(min(v.x, v.y), min(v.z, v.w)) != 0u);
    }
    __syncwarp();
}
__device__ __forceinline__ void ln_coeffs(float mean, float msq, uint32_t& r2, uint32_t& n2) {
    const float rs = bf_round(rsqrtf(fmaxf(msq - mean * mean, 0.f) + 1e-5f));
    r2 = pack2(rs, rs);
    n2 = pack2(-mean * rs, -mean * rs);
}

#define LOADW bulk_e(dst, g_wd + (size_t)((f >> 5) * 4 + nq) * 1792, 7168, bar);
template <int sec> __device__ __forceinline__ void ring_loader(const Params& p, uint32_t sb_, int r_, int j_, int lane) {
    const uint32_t sb = opaque(sb_);
    const int r = opaque(r_), j = opaque(j_), nq = j >> 1, fs = 4 * (j & 1) + nq;
    const int fa = pass_f(fs, 0), fb = pass_f(fs, 1), fc = pass_f(fs, 2);
    const uint32_t* h2src = (const uint32_t*)__shfl_sync(~0u, (unsigned long long)(p.actb + (size_t)r * RB_WORDS + RB_H2), 0);
    const CUtensorMap* gmap = (const CUtensorMap*)__shfl_sync(~0u, (unsigned long long)(&p.ga + sec), 0);
#define BAR(i) (sb + M_BAR + 8 * (i))
#define kh (j & 1)
            int sl = 0;
#pragma unroll 1
            for (int s = 0; s < 28; s++) {
                if (s == 7) { wait_flags(g_flag + (8 * r + j) * 128 + 96 + lane, lds1(sb + M_EPOCH) + 1, 0xFFFFu); fence_async_global(); }
                const int ps = s < 14 ? 0 : s < 21 ? 1 : 2;
                const uint32_t half = ps < 2 ? 8192 : 4096;
                const int sp = sl;
                if (s >= PACE && s < PACE_END) mbar_wait(BAR(B_FULL + s - PACE), 0);
                mbar_wait(BAR(B_EMPTY + sp), (s >= 7 && s < 14) || s >= 21);
                expect_e(BAR(B_FULL + sp), half);
                tma3_e(sb + slot_off(sp) + sec * half, gmap + 2 * ps, 0, ps ? 64 * sl : 32 * s, ps == 0 ? fa >> 6 : ps == 1 ? fb >> 6 : fc >> 5, BAR(B_FULL + sp));
                sl = sl == 6 ? 0 : sl + 1;
            }
            if (!sec) PROFH(3);
#pragma unroll 1
            for (int e = 0; e < 4; e++) {
                const uint32_t dst = sb + slot_off(e) + sec * 8192, bar = BAR(B_FULL + e);
                const int f = (e < 2 ? fa + 64 * e : e == 2 ? fb : fc) + 32 * sec;
                mbar_wait(BAR(B_EMPTY + e), 0);
                expect_e(bar, e == 3 && sec ? 0 : 7168);
                if (!(e == 3 && sec)) { LOADW }
            }
            sl = 4;
            int e = 4;
#pragma unroll 1
            for (int grp = 0; grp < 9; grp++) {
                const int ps = grp >= 6 ? 2 : grp >= 3 ? 1 : 0;
                int sidx = grp - 3 * ps;
                if (sec && sidx == 0) { mbar_wait(BAR(B_HRDY + ps), 0); fence_async_global(); }
                sidx += sidx >= nq;
                int f = pass_f(4 * kh + sidx, ps);
#pragma unroll 1
                for (int k = 4 >> ps; k > 0; k--, e++, f += 32) {
                    const uint32_t dst = sb + slot_off(sl), bar = BAR(B_FULL + sl);
                    mbar_wait(BAR(B_EMPTY + sl), e >= 12 && e < 24);
                    if (e < WIN_END && e >= WIN) mbar_wait(BAR(B_FULL + (sl >= WIN ? sl - WIN : sl + 12 - WIN)), e - WIN >= 12);
                    expect_e(bar, sec ? 8192 : 7168);
                    if (!sec) { LOADW }
                    else bulk_e(dst + 8192, h2src + f * 64, 8192, bar);
                    sl = sl == 11 ? 0 : sl + 1;
                }
            }
            if (!sec) PROFH(4);
}

#define PROF_PARAMS
#define PROF_ARGS
__device__ __noinline__ void helper_late(const Params& p, int r_, int j_, int warp_ PROF_PARAMS) {
    extern __shared__ __align__(1024) unsigned char smem[];
    const uint32_t sb = (uint32_t)__cvta_generic_to_shared(smem);
    const int r = opaque(r_), j = opaque(j_), warp = opaque(warp_), nq = j >> 1, b = 8 * r + j;
    uint32_t* const act = (uint32_t*)__shfl_sync(~0u, (unsigned long long)(p.actb + (size_t)r * RB_WORDS), 0);
    {
        const int lane = fresh_tid() & 31;
        const uint32_t target = lds1(sb + M_EPOCH) + 1;
        if (warp == 8) { expect_e(BAR(B_XCH), 14336); expect_e(BAR(B_XCH + 1), 14336); }
            if (warp == 9) {
#pragma unroll 1
                for (int kv = 0; kv < 2; kv++) {
                    mbar_wait(BAR(B_PUB + kv), 0);
                    wait_flags(g_flag + b * 128 + lane, target, (r >= 2 ? 6u : r == 1 ? 2u : 0u) << (8 * kv));
                    fence_async_global();
                    const uint32_t dst = sb + OFF_Y + (kv ? Y_VR : Y_K);
                    expect_e(BAR(B_KRFULL + kv), r >= 2 ? 28672 : r == 1 ? 14336 : 0);
                    if (r >= 2) bulk_e(dst, act - 2 * RB_WORDS + RB_KV + j * 7168 + kv * 3584, 14336, BAR(B_KRFULL + kv));
                    if (r >= 1) bulk_e(dst + 14336, act - RB_WORDS + RB_KV + j * 7168 + kv * 3584, 14336, BAR(B_KRFULL + kv));
                    if (kv == 0) { PROFH(8); }
                }
            } else if (warp == 8) {
                uint4 v[8];
                mbar_wait(BAR(B_WOFULL), 0);
#pragma unroll
                for (int k = 0; k < 8; k++) v[k] = ld_relaxed4(mod_src(lane + 32 * k, r, j, true));
#pragma unroll
                for (int k = 0; k < 8; k++) mod_store(sb, v[k], mod_src(lane + 32 * k, r, j, true), lane + 32 * k);
                warp_arrive(BAR(B_MOD1));
            } else if (warp == 11) {
                if (kh == 1 && r < 14) {
                    const uint32_t wmbuf = sb + OFF_X + HALF;
                    const int mcol = 2 * DM + 32 * (4 * r + nq);
                    mbar_wait(BAR(B_XFREE), 0);
                    tma3_e(wmbuf, &p.wm2, mcol, 0, 0, BAR(B_WMFULL));
                    tma3_e(wmbuf + 14336, &p.wm2, mcol, 224, 0, BAR(B_WMFULL));
#pragma unroll 1
                    for (int wd = lane; wd < 224; wd += 32) {
                        const uint32_t cb = __ldg((const uint32_t*)p.c + wd);
                        sts1(wmbuf + 28672 + (wd >> 3) * 32 + (wd & 3) * 8 + (wd & 4), pack2(silu_bf(cb & 0xFFFFu), silu_bf(cb >> 16)));
                    }
                    __syncwarp();
                    mbar_wait(BAR(B_WMFULL), 0);
                    const uint32_t wa = wmbuf + (8 * (lane >> 4) + (lane & 7)) * 64 + ((lane >> 3) & 1) * 16;
                    float d[2][4] = {};
#pragma unroll 4
                    for (int ks = 0; ks < 28; ks++) {
                        uint32_t A[8];
                        ldsm4t(wa + ks * 1024, A); ldsm4t(wa + ks * 1024 + 32, A + 4);
                        const float2 v = lds2f(wmbuf + 28672 + ks * 32 + (lane & 3) * 8);
                        mma16816(d[0], A[0], A[1], A[2], A[3], __float_as_uint(v.x), __float_as_uint(v.y));
                        mma16816(d[1], A[4], A[5], A[6], A[7], __float_as_uint(v.x), __float_as_uint(v.y));
                    }
                    const int q = lane & 3, col = mcol + 8 * q + (lane >> 2);
                    const uint32_t word = mod_word(q == 0 ? d[0][0] : q == 1 ? d[0][2] : q == 2 ? d[1][0] : d[1][2], col, target);
#pragma unroll
                    for (int i = 0; i < 8; i++) st_relaxed(g_mod + i * 6 * DM + col, word);
                }
                warp_arrive(BAR(B_WMFREE));
                mbar_wait(BAR(B_VRFULL), 0);
                l2_prefetch_e((const char*)p.wg + (size_t)b * 12544, 12544);
                l2_prefetch_e((const char*)p.wu + (size_t)b * 12544, 12544);
#pragma unroll 1
                for (int k = 0; k < (r < 12 ? 2 : 1); k++) {
                    const int u = 28 * kh + r + 16 * k;
                    expect_e(BAR(B_XFULL + k), 7168);
                    tma3_e(sb + OFF_Y + 102400, &p.dn, 0, 32 * u, 7 * j, BAR(B_XFULL + k));
                    tma3_e(sb + OFF_Y + 102400 + 3584, &p.dn, 0, 32 * u, 7 * (j ^ 1), BAR(B_XFULL + k));
                    mbar_wait(BAR(B_XFULL + k), 1);
                    asm volatile("{\n.reg .pred p;\nelect.sync _|p, 0xffffffff;\n@p cp.async.bulk.global.shared::cta.bulk_group [%0], [%1], 7168;\n"
                                 "cp.async.bulk.commit_group;\ncp.async.bulk.wait_group 0;\n}" ::"l"(g_wd + (size_t)(u * 4 + nq) * 1792), "r"(sb + OFF_Y + 102400) : "memory");
                    __syncwarp();
                }
                warp_arrive(BAR(B_FULLK));
                fence_gpu();
                if (lane < 16) st_relaxed(g_flag + (8 * lane + j) * 128 + 96 + r, target);
            }
        if (warp == 8 || warp == 11) {
            const int sec = warp == 11;
            if (sec) ring_loader<1>(p, sb, r, j, lane); else ring_loader<0>(p, sb, r, j, lane);
            mbar_wait(BAR(B_DONE), 0);
        } else if (warp == 9) {
#pragma unroll
            for (int ev = 0; ev < 4; ev++) { expect_e(BAR(B_GFULL + ev), ev < 2 ? HALF / 2 : 16384 + 4096); expect_e(BAR(B_XFULL + 2 + ev), ev < 2 ? HALF / 2 : HALF - 16384); }
            mbar_wait(BAR(B_PUB + 2), 0);
            const uint32_t* fp = g_flag + b * 128 + 32 + lane;
            const int par = (target - 1) & 1;
#pragma unroll 1
            for (int n = 0, ev = 0; ev < 4; n++) {
                if (ev == 1) mbar_wait(BAR(B_PUB + 3), 0);
                uint32_t ok = __ballot_sync(~0u, (int)(ld_relaxed(fp) - target) >= 0) >> (8 * ev);
                while ((ok & 0xFFu) == 0xFFu) {
                    if (ev == 1) mbar_wait(BAR(B_FULLK), 1);
                    asm volatile("fence.acquire.gpu;" ::: "memory");
                    fence_async_global();
                    const int tile = (ev & 1) + (ev >> 1) * par * 2;
                    const uint32_t dst = sb + (ev == 0 ? OFF_X : OFF_Y + (ev & 1) * HALF), first = ev < 2 ? HALF / 2 : 16384;
                    const char* src = (const char*)(act + RB_O + ((ev >> 1) * 2 + tile) * 14336);
                    if (ev >= 2) bulk_e(sb + OFF_X + X_STAT + (ev & 1) * 49152, act + RB_ST + tile * 1024, 4096, BAR(B_GFULL + ev));
                    bulk_e(dst, src, first, BAR(B_GFULL + ev));
                    bulk_e(dst + first, src + first, HALF - first, BAR(B_XFULL + 2 + ev));
                    if (ev) PROFH(4 + ev);
                    ev++; ok >>= 8;
                }
                if (n > SPIN_LIMIT) __trap();
            }
            mbar_wait(BAR(B_XFULL + 5), 1);
#pragma unroll 1
            for (int hf = 0; hf < 2; hf++) {
                const int tile = (par ^ 1) * 2 + hf;
                uint4* xz = (uint4*)(act + RB_X1 + tile * 14336 + j * 1792) + lane;
#pragma unroll
                for (int i = 0; i < 14; i++) xz[i * 32] = make_uint4(0, 0, 0, 0);
                ((uint4*)(act + RB_ST + (tile * 8 + j) * 128))[lane] = make_uint4(0, 0, 0, 0);
            }
#pragma unroll 1
            for (int ps = 0; ps < 3; ps++) {
                mbar_wait(BAR(B_PUB + 6 + ps), 0);
                wait_flags(g_flag + b * 128 + 64 + lane, target, (0x55u << kh) << (8 * ps));
                warp_arrive(BAR(B_HRDY + ps));
                PROFH(9 + ps);
            }
        } else {
#pragma unroll 1
            for (int k = 0; k < 9; k++) {
                uint32_t* fp = k < 2 ? g_flag + (b + 8 * lane) * 128 + k * 8 + lane : g_flag + (8 * r + lane) * 128 + 16 + k * 8 + j;
                mbar_wait(BAR(B_PUB + k), 0);
                if (k != 4 && k != 5) fence_gpu();
                if (k < 2 ? (lane == 1 || lane == 2) : lane < 8) st_relaxed(fp, target);
                if (k >= 3 && k <= 5) PROFH(k - 3);
            }
        }
    }
}

__global__ void __cluster_dims__(2, 1, 1) __launch_bounds__(384, 1) fused_block_kernel(const __grid_constant__ Params p) {
    extern __shared__ __align__(1024) unsigned char smem[];
    const uint32_t sb = (uint32_t)__cvta_generic_to_shared(smem);
    const int tid = threadIdx.x, lane = tid & 31, warp = __shfl_sync(~0u, tid >> 5, 0);
    const int m = blockIdx.x >> 1;
    int r, nq;
    if (m < 4) { r = 15; nq = m; }
    else if (m < 36) { r = (m - 4) & 7; nq = (m - 4) >> 3; }
    else { nq = (m - 36) / 7; r = m - 28 - 7 * nq; }
    const int j = opaque(2 * nq + (blockIdx.x & 1)), b = 8 * r + j, fs = 4 * kh + nq;
#define act (p.actb + (size_t)r * RB_WORDS)
    constexpr uint32_t sc = 0;
    if (lane == 0 && warp < 9 && warp != 6 && warp != 7) {
        const int i0 = warp == 8 ? 0 : 8 + 8 * warp, cnt = warp == 0 || warp == 8 ? 1 : warp < 3 ? 2 : 8;
#pragma unroll
        for (int k = 0; k < 8; k++) if (i0 + k != B_WMFULL) mbar_init(BAR(i0 + k), cnt);
        if (warp == 8) mbar_init(BAR(B_WMFULL), 1);
        asm volatile("fence.mbarrier_init.release.cluster;" ::: "memory");
        fence_async_smem();
    }

    if (warp >= 8) {
        const int lane = fresh_tid() & 31;
        const bool early = kh == 0, gemv = r < 14;
        const int mcol = early ? 16 * (4 * r + nq) : 2 * DM + 32 * (4 * r + nq);
        const uint32_t wmbuf = sb + OFF_Y + HALF;
        if (warp == 8) {
            __syncwarp();
            expect_e(BAR(B_WMFULL), gemv ? 28672 >> early : 0);
            if (early && gemv) { tma3_e(wmbuf, &p.wm, mcol, 0, 0, BAR(B_WMFULL)); tma3_e(wmbuf + 7168, &p.wm, mcol, 224, 0, BAR(B_WMFULL)); }
#pragma unroll
            for (int kb = 0; kb < XFIRST; kb++) {
                expect_e(BAR(B_XFULL + kb), 16384);
                tma3_e(sb + OFF_X + kb * 16384, &p.xm, 64 * kb, 128 * r, 0, BAR(B_XFULL + kb));
            }
        }
        asm volatile("setmaxnreg.dec.sync.aligned.u32 56;");
        if (warp == 9) {
#pragma unroll
            for (int i = 56; i < 64; i++) init_e(BAR(i), 1);
            fence_async_smem();
        }
        bar_arrive(0, 384);
        asm volatile("barrier.cluster.arrive.relaxed.aligned;" ::: "memory");
        if (warp == 8) {
#pragma unroll
            for (int kb = XFIRST; kb < 7; kb++) {
                expect_e(BAR(B_XFULL + kb), 16384);
                tma3_e(sb + OFF_X + kb * 16384, &p.xm, 64 * kb, 128 * r, 0, BAR(B_XFULL + kb));
            }
            if (KDELAY >= 0) { mbar_wait(BAR(B_XFULL + KDELAY), 0); l2_prefetch_e((const char*)p.wqkv + (size_t)b * 9408, 9408); }
#pragma unroll 1
            for (int mt = 0; mt < 4; mt++) {
                if (mt == 1) bar_sync(9, 384);
                if (mt == 3) mbar_wait(BAR(B_WMFREE), 0);
                if (mt) mbar_wait(BAR(mt == 1 ? B_MOD1 : mt == 2 ? B_XFREE : B_VRFULL), 0);
                const uint32_t bar = BAR(mt == 3 ? B_WOFULL : B_FULLK + mt), dst = sb + (mt < 2 ? OFF_Y : OFF_X) + (mt & 1) * HALF;
                const int c0 = (mt < 2 ? DM + DM * mt : 0) + 56 * j - 8 * kh;
                if (!sc) {
                    expect_e(bar, HALF);
                    tma3_e(dst, mt == 3 ? &p.wo : &p.qkv, c0, 0, 0, bar);
                    tma3_e(dst + HALF / 2, mt == 3 ? &p.wo : &p.qkv, c0, 224, 0, bar);
                }
            }
        } else {
            if (KDELAY < 0 && warp == 10) l2_prefetch_e((const char*)p.wqkv + (size_t)b * 9408, 9408);
            bar_sync(9, 384);
            if (sc) return;
            if (warp == 11 && early) {
                const uint32_t target = lds1(sb + M_EPOCH) + 1;
                mbar_wait(BAR(B_GEMV), 0);
                float sum = 0.f;
#pragma unroll
                for (int i = 0; i < 8; i++) sum += *(const float*)(smem + OFF_Y + HALF + 29696 + (i * 16 + (lane & 15)) * 4);
                uint32_t* mg = g_mod + mcol + (lane & 15) + (lane >> 4) * 4 * 6 * DM;
                const uint32_t word = mod_word(sum, mcol, target);
                if (gemv) { st_relaxed(mg, word); st_relaxed(mg + 6 * DM, word); st_relaxed(mg + 12 * DM, word); st_relaxed(mg + 18 * DM, word); }
            }
        }
    }
    if (LIKELY(warp < 8)) {
        const int w = warp >> 2, wi = warp & 3;
#define COORDS const int t = fresh_tid() & 127, lane = t & 31, q = lane & 3, lr = lane >> 2, ra = 64 * w + 16 * wi + lr; \
        const uint32_t lx = (lane >> 4) ^ (lane & 7), mrow = (64 * w + 16 * wi + ((lane >> 3) & 1) * 8 + (lane & 7)) * 128; \
        (void)q; (void)lr; (void)ra; (void)lx; (void)mrow;
        const int sid = 2 * (j & 3) + w;
#define RUN(k) (!sc || sid == (k))
#define WAIT(i, par) mbar_wait_c(BAR(i), (par) | sc)
        constexpr uint64_t DB128 = dconst(4096, 1024, 1);
        {
            const int wd = fresh_tid();
            const uint32_t cb = wd < 224 ? __ldg((const uint32_t*)p.c + wd) : 0u;
            if (wd == 255 && !sc) sts1(sb + M_EPOCH, atomicAdd(&g_ticket, 1u) / NCTA);
            sts1(sb + OFF_Y + HALF + 28672 + (wd >> 3) * 32 + (wd & 3) * 8 + (wd & 4), pack2(silu_bf(cb & 0xFFFFu), silu_bf(cb >> 16)));
        }
        bar_arrive(9, 384);
        bar_sync(0, 384);
        asm volatile("barrier.cluster.arrive.relaxed.aligned;" ::: "memory");
        asm volatile("setmaxnreg.inc.sync.aligned.u32 224;");
        PROFC(0);
        uint32_t xr[16];
        {
            COORDS
            uint32_t h[112];
            uint32_t ra2, na2, rb2, nb2;
            const int mi = min(128 * w + t, 223);
            const uint4* msrc = mod_src(mi, r, j, false);
            uint4 mv;
            {
                float ds[4] = {}, da[2][4] = {}, db[2][4] = {};
                const uint32_t ONE2 = 0x3F803F80u;
#pragma unroll
                for (int kb = 0; kb < 7; kb++) {
                    if (kb == GEMV_AT && kh == 0) { WAIT(B_WMFULL, 0); gemv_part(sb + OFF_Y + HALF, warp, lane); warp_arrive(BAR(B_GEMV)); }
                    WAIT(B_XFULL + kb, 0);
#pragma unroll
                    for (int k4 = 0; k4 < 4; k4++) ldsm4(sb + OFF_X + mrow + kb * 16384 + (((2 * k4) ^ lx) << 4), h + 16 * kb + 4 * k4);
#pragma unroll
                    for (int k4 = 0; k4 < 4; k4++) {
                        const uint32_t* f = h + 16 * kb + 4 * k4;
                        mma16816(ds, f[0], f[1], f[2], f[3], ONE2, ONE2);
                        mma1688(da[0], f[0], f[1], f[0]); mma1688(db[0], f[0], f[1], f[1]);
                        mma1688(da[1], f[2], f[3], f[2]); mma1688(db[1], f[2], f[3], f[3]);
                    }
                }
#pragma unroll
                for (int i = 0; i < 4; i++) {
                    const int ch = 7 * j + 2 * i + (lane >> 4);
                    ldsm4(sb + OFF_X + mrow + (ch >> 3) * 16384 + (((ch ^ lane) & 7) << 4), xr + 4 * i);
                }
                mv = ld_relaxed4(msrc);
                warp_arrive(BAR(B_XFREE));
                float qa = (lr & 1) ? da[0][1] + da[1][1] : da[0][0] + da[1][0];
                float qb = (lr & 1) ? db[0][3] + db[1][3] : db[0][2] + db[1][2];
                const int src = (lane & ~3) | (lr >> 1);
                qa = __shfl_sync(~0u, qa, src);
                qb = __shfl_sync(~0u, qb, src);
                ln_coeffs(ds[0] * (1.f / DM), qa * (1.f / DM), ra2, na2);
                ln_coeffs(ds[2] * (1.f / DM), qb * (1.f / DM), rb2, nb2);
#pragma unroll
                for (int i = 0; i < 4 * NPRE; i += 2) { h[i] = hfma2(h[i], ra2, na2); h[i + 1] = hfma2(h[i + 1], rb2, nb2); }
            }
            PROFC(1);
            {
                float ak[28], av[28], aq[28];
                uint32_t kp[14], vp[14];
                const uint64_t bq0 = (DB128 & ~0xFFFFFFFFull) | (mkdesc(sb + OFF_X, DB128) + kh), bk0 = bq0 + (OFF_Y >> 4), bv0 = bk0 + (HALF >> 4);
                uint32_t* kvg = act + RB_KV + j * 7168 + (8 * w + 2 * wi) * 224 + lane;
                mod_store(sb, mv, msrc, mi);
                bar_sync(3, 256);
                if (warp == 0) warp_arrive(BAR(B_MOD1));
                WAIT(B_FULLK, 0);
                PROFC(2);
                reg_def<28>(ak);
#pragma unroll
                for (int g4 = 0; g4 < 4; g4++) {
#pragma unroll
                    for (int ks = 7 * g4; ks < 7 * g4 + 7; ks++) {
                        const uint4 st = *(const uint4*)(smem + M_ST + ks * 64 + q * 16);
                        if (ks >= NPRE) {
                            h[4 * ks] = hfma2(h[4 * ks], ra2, na2); h[4 * ks + 1] = hfma2(h[4 * ks + 1], rb2, nb2);
                            h[4 * ks + 2] = hfma2(h[4 * ks + 2], ra2, na2); h[4 * ks + 3] = hfma2(h[4 * ks + 3], rb2, nb2);
                        }
                        h[4 * ks] = hfma2(h[4 * ks], st.x, st.y); h[4 * ks + 1] = hfma2(h[4 * ks + 1], st.x, st.y);
                        h[4 * ks + 2] = hfma2(h[4 * ks + 2], st.z, st.w); h[4 * ks + 3] = hfma2(h[4 * ks + 3], st.z, st.w);
                    }
                    WG_FENCE();
#pragma unroll
                    for (int ks = 7 * g4; ks < 7 * g4 + 7; ks++) wgmma_rl_56(ak, h[4 * ks], h[4 * ks + 1], h[4 * ks + 2], h[4 * ks + 3], bk0 + ks * 128, ks != 0);
                }
                WG_COMMIT();
                PROFC(3);
                reg_def<28>(av);
                WG_WAIT(0);
                reg_fence<28>(ak);
#pragma unroll
                for (int g = 0; g < 7; g++) {
                    kp[2 * g] = pack2(ak[4 * g], ak[4 * g + 1]); kp[2 * g + 1] = pack2(ak[4 * g + 2], ak[4 * g + 3]);
                    kvg[g * 32] = kp[2 * g]; kvg[224 + g * 32] = kp[2 * g + 1];
                }
                warp_arrive(BAR(B_PUB));
                PROFC(4);
                if (KEARLY) WAIT(B_FULLV, 0);
                WG_FENCE();
#pragma unroll
                for (int ks = KEARLY ? 0 : 8; ks < 28; ks++) wgmma_rl_56(av, h[4 * ks], h[4 * ks + 1], h[4 * ks + 2], h[4 * ks + 3], bv0 + ks * 128, ks != 0);
                WG_COMMIT();
                WAIT(B_FULLQ, 0);
                reg_def<28>(aq);
                WG_FENCE();
#pragma unroll
                for (int ks = 0; ks < 8; ks++) wgmma_rl_56(aq, h[4 * ks], h[4 * ks + 1], h[4 * ks + 2], h[4 * ks + 3], bq0 + ks * 128, ks != 0);
                WG_COMMIT();
                WG_WAIT(1);
                reg_fence<28>(av);
#pragma unroll
                for (int g = 0; g < 7; g++) {
                    vp[2 * g] = pack2(av[4 * g], av[4 * g + 1]); vp[2 * g + 1] = pack2(av[4 * g + 2], av[4 * g + 3]);
                    kvg[3584 + g * 32] = vp[2 * g]; kvg[3584 + 224 + g * 32] = vp[2 * g + 1];
                }
                warp_arrive(BAR(B_PUB + 1));
                PROFC(5);
                WG_FENCE();
#pragma unroll
                for (int ks = 8; ks < 28; ks++) wgmma_rl_56(aq, h[4 * ks], h[4 * ks + 1], h[4 * ks + 2], h[4 * ks + 3], bq0 + ks * 128, 1);
                WG_COMMIT();
                WAIT(B_PUB + 1, 0);
                const uint32_t rg = 8 * w + 2 * wi + ((lane >> 3) & 1);
                const uint32_t ko = sb + OFF_Y + Y_KOWN + rg * 896 + (lane & 7) * 16, qo = sb + OFF_Y + Y_Q + rg * 1024 + (lane >> 4) * 128 + (lane & 7) * 16;
#pragma unroll
                for (int g = 0; g < 6; g += 2) {
                    stsm4(ko + (g + (lane >> 4)) * 128, kp[2 * g], kp[2 * g + 1], kp[2 * g + 2], kp[2 * g + 3]);
                    stsm4(ko + (Y_VOWN - Y_KOWN) + (g + (lane >> 4)) * 128, vp[2 * g], vp[2 * g + 1], vp[2 * g + 2], vp[2 * g + 3]);
                }
                stsm4(ko + (lane >> 4) * (Y_VOWN - Y_KOWN) + 6 * 128, kp[12], kp[13], vp[12], vp[13]);
                WG_WAIT(0);
                reg_fence<28>(aq);
                __syncwarp();
                if (lane < 3 && w == 1) mbar_arrive(BAR(B_EMPTY + lane));
                uint32_t qp[14];
#pragma unroll
                for (int i = 0; i < 14; i++) qp[i] = pack2(aq[2 * i], aq[2 * i + 1]);
                stsm4(qo, qp[0], qp[1], qp[2], qp[3]);
                stsm4(qo + 256, qp[4], qp[5], q < 2 ? qp[6] : 0u, q < 2 ? qp[7] : 0u);
                stsm4(qo + 512, q < 2 ? 0u : qp[6], q < 2 ? 0u : qp[7], qp[8], qp[9]);
                stsm4(qo + 768, qp[10], qp[11], qp[12], qp[13]);
                if (!sc) bar_sync(3, 256);
            }
        }
        PROFC(6);
        WAIT(B_KRFULL, 0);
        if (ATT_OFF && w == ATT_WG) { const uint32_t t0 = clock(); while (clock() - t0 < ATT_OFF) {} }
        PROFC(7);
        if (RUN(2)) {
#pragma unroll 1
            for (int hf = sc; hf < 2; hf++) {
                COORDS
                float s[136];
                float na = 0.f, nb = 0.f;
                const float CS = 0.18898223650461361f * 1.4426950408889634f;
                const int kg0 = 8 * hf + 2 * wi;
                const int pmin = 16 - 8 * r - 4 * hf - wi;
                const float NEG = __int_as_float(0xFF800000);
                {
                    uint32_t F[8];
                    const uint32_t qa = sb + OFF_Y + Y_Q + (kg0 + ((lane >> 3) & 1)) * 1024 + (4 * w + (lane >> 4)) * 128 + (lane & 7) * 16;
                    ldsm4(qa, F); ldsm4(qa + 256, F + 4);
                    uint32_t ka = sb + OFF_Y + Y_K + kg0 * 896 + (3 * w + (lane >> 3)) * 128 + (lane & 7) * 16;
#pragma unroll
                    for (int g = 0; g < 34; g++) {
                        uint32_t B[4];
                        if (g >= 12 && g % 4 == 0) ka += __float_as_uint(s[4 * (g - 12)]) & p.zero;
                        ldsm4(ka + g * 896, B);
                        mma16816_first(s + 4 * g, F[0], F[1], F[2], F[3], B[0], B[1]);
                        mma16816_v(s + 4 * g, F[4], F[5], F[6], F[7], B[2], B[3]);
                    }
                    const bool c0 = 2 * q > lr, c1 = 2 * q + 1 > lr;
                    if (!c0) { s[0] = NEG; s[6] = NEG; }
                    if (!c1) { s[1] = NEG; s[7] = NEG; }
                    s[2] = NEG; s[3] = NEG;
                    if (c0) { s[128] = NEG; s[134] = NEG; }
                    if (c1) { s[129] = NEG; s[135] = NEG; }
                    s[132] = NEG; s[133] = NEG;
                    float ma = NEG, mb = NEG;
#pragma unroll
                    for (int pp = 0; pp < 17; pp++) {
                        const float* e = s + 8 * pp;
                        const float bias = pp < pmin ? NEG : 0.f;
                        ma = fmaxf(ma, fmaxf(fmaxf(e[0], e[1]), fmaxf(e[4], e[5])) + bias);
                        mb = fmaxf(mb, fmaxf(fmaxf(e[2], e[3]), fmaxf(e[6], e[7])) + bias);
                    }
                    ma = fmaxf(ma, __shfl_xor_sync(~0u, ma, 1)); mb = fmaxf(mb, __shfl_xor_sync(~0u, mb, 1));
                    ma = fmaxf(ma, __shfl_xor_sync(~0u, ma, 2)); mb = fmaxf(mb, __shfl_xor_sync(~0u, mb, 2));
                    na = -ma * CS; nb = -mb * CS;
                }
                PROFC(8 + 3 * hf);
                {
                    WAIT(B_VRFULL, 0);
                    float o[16] = {}, rs[4] = {};
                    uint32_t pk[2];
                    const uint32_t va = sb + OFF_Y + Y_VR + (kg0 + ((lane >> 3) & 1)) * 896 + (3 * w + (lane >> 4)) * 128 + (lane & 7) * 16;
#pragma unroll
                    for (int pp = 0; pp < 17; pp++) {
                        uint32_t B[8];
                        const uint32_t v = va + pp * 1792 + (pp == 16 || (pp >= 9 && kg0 + 2 * pp >= 32) ? Y_VOWN - 32 * 896 : 0);
                        ldsm4t(v, B); ldsm4t(v + 256, B + 4);
                        float e[8];
                        const float bias = __uint_as_float((pp < pmin ? 0xFF800000u : 0u) | ((pp < 2 ? B[0] : pk[pp & 1]) & p.zero));
#pragma unroll
                        for (int i = 0; i < 8; i++) e[i] = ex2(fmaf(s[8 * pp + i], CS, ((i & 2) ? nb : na) + bias));
                        const uint32_t p0 = pack2(e[0], e[1]), p1 = pack2(e[2], e[3]), p2 = pack2(e[4], e[5]), p3 = pack2(e[6], e[7]);
                        pk[pp & 1] = p3;
                        mma16816(rs, p0, p1, p2, p3, 0x3F803F80u, 0x3F803F80u);
#pragma unroll
                        for (int g = 0; g < 4; g++) mma16816(o + 4 * g, p0, p1, p2, p3, B[2 * g], B[2 * g + 1]);
                    }
                    PROFC(9 + 3 * hf);
                    const float ia = rcp(rs[0]), ib = rcp(rs[2]);
                    uint32_t* og = act + RB_O + hf * 14336 + (7 * j + 3 * w) * 256 + wi * 64 + lane;
#pragma unroll
                    for (int g = 0; g < 4; g++) {
                        if ((g == 3 - 3 * w) ? ((q >> 1) == w) : true) {
                            og[g * 256] = pack2(o[4 * g] * ia, o[4 * g + 1] * ia);
                            og[g * 256 + 32] = pack2(o[4 * g + 2] * ib, o[4 * g + 3] * ib);
                        }
                    }
                    warp_arrive(BAR(B_PUB + 2 + hf));
                    PROFC(10 + 3 * hf);
                }
            }
        }
        uint32_t x1p[14];
        COORDS
        constexpr uint64_t DT = dconst(1024, 128, 0);
        const int tile = opaque((lds1(sb + M_EPOCH) & 1) * 2 + w);
        if (RUN(4)) {
            float ac[28];
            const uint32_t ad = mkdesc(sb + (w ? OFF_Y + HALF : OFF_X), DT), bd = mkdesc(sb + OFF_X + HALF, DB128) + kh;
            WAIT(B_WOFULL, 0);
            WAIT(B_MOD1, 1);
            WAIT(B_GFULL + w, 0);
            PROFC(28);
            reg_def<28>(ac);
#pragma unroll 1
            for (int u = 0; u < 4; u++) {
                if (u == 2) WAIT(B_XFULL + 2 + w, 1);
                WG_FENCE();
#pragma unroll
                for (int i = 0; i < 7; i++) wgmma_ss_56<DT, DB128>(ac, ad + (7 * u + i) * 128, bd + (7 * u + i) * 128, (u | i) != 0);
            }
            WG_COMMIT();
            WG_WAIT(0);
            reg_fence<28>(ac);
            PROFC(14);
            __syncwarp();
            if (lane < 3) mbar_arrive(BAR(B_EMPTY + 4 - w + lane));
            if (lane < 3 && w == 0) mbar_arrive(BAR(B_EMPTY + lane));
            float ds[4] = {}, da[4] = {}, db[4] = {};
            uint32_t* xo = act + RB_X1 + tile * 14336 + 7 * j * 256 + wi * 64 + lane;
#pragma unroll
            for (int g = 0; g < 7; g++) {
                const float2 ga = *(const float2*)(smem + M_G + (8 * g + 2 * q) * 4);
                x1p[2 * g] = pack2(fmaf(ga.x, ac[4 * g], bf_lo(xr[2 * g])), fmaf(ga.y, ac[4 * g + 1], bf_hi(xr[2 * g])));
                x1p[2 * g + 1] = pack2(fmaf(ga.x, ac[4 * g + 2], bf_lo(xr[2 * g + 1])), fmaf(ga.y, ac[4 * g + 3], bf_hi(xr[2 * g + 1])));
                st_relaxed(xo + g * 256, nz(x1p[2 * g])); st_relaxed(xo + g * 256 + 32, nz(x1p[2 * g + 1]));
                mma1688(ds, x1p[2 * g], x1p[2 * g + 1], 0x3F803F80u);
                mma1688(da, x1p[2 * g], x1p[2 * g + 1], x1p[2 * g]);
                mma1688(db, x1p[2 * g], x1p[2 * g + 1], x1p[2 * g + 1]);
            }
            const int src = (lane & ~3) | (lr >> 1);
            const float qa = __shfl_sync(~0u, (lr & 1) ? da[1] : da[0], src), qb = __shfl_sync(~0u, (lr & 1) ? db[3] : db[2], src);
            const float kk = (q & 1) ? ((q & 2) ? qb : qa) : ((q & 2) ? ds[2] : ds[0]);
            st_relaxed(act + RB_ST + ((tile * 8 + j) * 64 + 16 * wi + lr + 4 * (q & 2)) * 2 + (q & 1), nz(__float_as_uint(kk)));
            __syncwarp();
            if (lane < 2) mbar_arrive(BAR(B_PUB + 4 + w));
        } else reg_def<14>(x1p);
        PROFC(15);
        uint32_t h2a[32], h2b[24];
        {
            const int fa = pass_f(fs, 0), fb = pass_f(fs, 1), fc = pass_f(fs, 2);
            uint32_t* h2g = act + RB_H2 + (8 * w + 2 * wi) * 32 + lane;
            const uint32_t a0 = mkdesc(sb + OFF_Y + w * HALF, DT);
            if (RUN(3)) {
                uint32_t ra2, na2, rb2, nb2;
                {
                    const uint32_t* sg = act + RB_ST + ((tile * 8 + 2 * q) * 64 + 16 * wi + lr) * 2;
                    uint2 u[4];
                    WAIT(B_GFULL + 2 + w, 0);
                    PROFC(16);
#pragma unroll
                    for (int i = 0; i < 4; i++) { const float2 v = lds2f(sb + OFF_X + X_STAT + w * 49152 + ((2 * q + (i >> 1)) * 64 + 16 * wi + lr + 8 * (i & 1)) * 8); u[i] = make_uint2(__float_as_uint(v.x), __float_as_uint(v.y)); }
                    while (__any_sync(~0u, min(min(min(u[0].x, u[0].y), min(u[1].x, u[1].y)), min(min(u[2].x, u[2].y), min(u[3].x, u[3].y))) < 1u - sc)) {
#pragma unroll
                        for (int i = 0; i < 4; i++) u[i] = ld_relaxed2(sg + (i >> 1) * 128 + (i & 1) * 16);
                    }
                    warp_arrive(BAR(B_EMPTY + 3 + 3 * w));
                    float v[4] = {__uint_as_float(u[0].x) + __uint_as_float(u[2].x), __uint_as_float(u[0].y) + __uint_as_float(u[2].y),
                                  __uint_as_float(u[1].x) + __uint_as_float(u[3].x), __uint_as_float(u[1].y) + __uint_as_float(u[3].y)};
#pragma unroll
                    for (int i = 0; i < 4; i++) { v[i] += __shfl_xor_sync(~0u, v[i], 1); v[i] += __shfl_xor_sync(~0u, v[i], 2); }
                    ln_coeffs(v[0] * (1.f / DM), v[1] * (1.f / DM), ra2, na2);
                    ln_coeffs(v[2] * (1.f / DM), v[3] * (1.f / DM), rb2, nb2);
                }
                const uint32_t ha = sb + OFF_Y + w * HALF + (lane >> 4) * 1024 + (2 * wi + ((lane >> 3) & 1)) * 128 + (lane & 7) * 16;
                const uint32_t sta = sb + M_ST + q * 16;
                const uint32_t* xg = act + RB_X1 + tile * 14336 + (lane >> 4) * 256 + wi * 64 + (lane & 15) * 4;
                uint32_t x[8];
                const uint32_t xs = sb + OFF_Y + w * HALF + (lane >> 4) * 1024 + wi * 256 + (lane & 15) * 16;
                uint4 st[2];
                auto load = [&](int s) {
                    if (s == 4) mbar_wait_c(BAR(B_XFULL + 4 + w), 1);
                    ldsm4(ha + s * 4096, x); ldsm4(ha + s * 4096 + 2048, x + 4);
                    st[0] = lds4(sta + s * 128); st[1] = lds4(sta + s * 128 + 64);
                };
                auto prep = [&](int s, uint32_t* f) {
                    if (__any_sync(~0u, min(min(min(x[0], x[1]), min(x[2], x[3])), min(min(x[4], x[5]), min(x[6], x[7]))) < 1u - sc)) {
                        WG_WAIT(0);
                        x1_fix(xg, xs, s);
                        ldsm4(ha + s * 4096, x); ldsm4(ha + s * 4096 + 2048, x + 4);
                    }
#pragma unroll
                    for (int i = 0; i < 2; i++) {
                        f[4 * i] = hfma2(hfma2(x[4 * i], ra2, na2), st[i].x, st[i].y); f[4 * i + 1] = hfma2(hfma2(x[4 * i + 1], rb2, nb2), st[i].x, st[i].y);
                        f[4 * i + 2] = hfma2(hfma2(x[4 * i + 2], ra2, na2), st[i].z, st[i].w); f[4 * i + 3] = hfma2(hfma2(x[4 * i + 3], rb2, nb2), st[i].z, st[i].w);
                    }
                    if (s < 13) load(s + 1);
                    stsm4(ha + s * 4096, f[0], f[1], f[2], f[3]); stsm4(ha + s * 4096 + 2048, f[4], f[5], f[6], f[7]);
                };
                float ac[128];
                uint32_t fr[3][8];
                uint64_t bd = (DB128 & ~0xFFFFFFFFull) | mkdesc(sb, DB128);
                reg_def<128>(ac);
                load(0);
                prep(0, fr[0]);
                PROFC(17);
#pragma unroll
                for (int s = 0; s < 14; s++) {
                    const uint32_t* f = fr[s % 3];
                    WAIT(B_FULL + g1_slot(s), s >= 7);
                    WG_FENCE();
                    wgmma_rl_256(ac, f[0], f[1], f[2], f[3], bd, s != 0);
                    wgmma_rl_256(ac, f[4], f[5], f[6], f[7], bd + 128, 1);
                    bd += s == 6 ? p.zero - 6 * 1024ull : 1024;
                    WG_COMMIT();
                    if (s < 13) prep(s + 1, fr[(s + 1) % 3]);
                    if (s > 0) { WG_WAIT(1); warp_arrive(BAR(B_EMPTY + g1_slot(s - 1))); }
                }
                fence_async_smem();
                PROFC(18);
                WG_WAIT(0);
                reg_fence<128>(ac);
                warp_arrive(BAR(B_EMPTY + 6));
#pragma unroll
                for (int g = 0; g < 16; g++) {
                    h2a[2 * g] = hmul2(pack2_relu(ac[4 * g], ac[4 * g + 1]), pack2(ac[64 + 4 * g], ac[64 + 4 * g + 1]));
                    h2a[2 * g + 1] = hmul2(pack2_relu(ac[4 * g + 2], ac[4 * g + 3]), pack2(ac[64 + 4 * g + 2], ac[64 + 4 * g + 3]));
                }
                bar_sync(1 + w, 128);
            } else reg_def<32>(h2a);
            PROFC(19);
            if (RUN(5)) {
                float ac[64];
                reg_def<64>(ac);
                const uint32_t bx = mkdesc(sb, dconst(8192, 1024, 1));
#pragma unroll kB
                for (int s = 0; s < 7; s++) {
                    WAIT(B_FULL + s, 0);
                    const uint32_t ad = a0 + s * 512, bd = bx + (slot_off(s) >> 4);
                    WG_FENCE();
#pragma unroll
                    for (int k = 0; k < 4; k++) wgmma_ss_128<DT, DB128>(ac, ad + k * 128, bd + k * 128, (s | k) != 0);
                    WG_COMMIT();
                    if (s == 1) {
#pragma unroll
                        for (int g = 0; g < 16; g++) { h2g[(fa / 8 + g) * 512] = h2a[2 * g]; h2g[(fa / 8 + g) * 512 + 32] = h2a[2 * g + 1]; }
                        warp_arrive(BAR(B_PUB + 6));
                    }
                    if (s > 0) { WG_WAIT(1); warp_arrive(BAR(B_EMPTY + s - 1)); }
                }
                WG_WAIT(0);
                reg_fence<64>(ac);
                warp_arrive(BAR(B_EMPTY + 6));
#pragma unroll
                for (int g = 0; g < 8; g++) {
                    h2b[2 * g] = hmul2(pack2_relu(ac[4 * g], ac[4 * g + 1]), pack2(ac[32 + 4 * g], ac[32 + 4 * g + 1]));
                    h2b[2 * g + 1] = hmul2(pack2_relu(ac[4 * g + 2], ac[4 * g + 3]), pack2(ac[32 + 4 * g + 2], ac[32 + 4 * g + 3]));
                }
            } else reg_def<16>(h2b);
            PROFC(27);
            if (RUN(6)) {
                float ac[32];
                reg_def<32>(ac);
                const uint32_t bx = mkdesc(sb, dconst(4096, 512, 2));
#pragma unroll kC
                for (int s = 0; s < 7; s++) {
                    WAIT(B_FULL + s, 1);
                    const uint32_t ad = a0 + s * 512, bd = bx + (slot_off(s) >> 4);
                    WG_FENCE();
#pragma unroll
                    for (int k = 0; k < 4; k++) wgmma_ss_64<DT, dconst(4096, 512, 2)>(ac, ad + k * 128, bd + k * 64, (s | k) != 0);
                    WG_COMMIT();
                    if (s == 1) {
#pragma unroll
                        for (int g = 0; g < 8; g++) { h2g[(fb / 8 + g) * 512] = h2b[2 * g]; h2g[(fb / 8 + g) * 512 + 32] = h2b[2 * g + 1]; }
                        warp_arrive(BAR(B_PUB + 7));
                    }
                    if (s > 0) { WG_WAIT(1); warp_arrive(BAR(B_EMPTY + s - 1)); }
                }
                WG_WAIT(0);
                reg_fence<32>(ac);
                __syncwarp();
                if (lane < 6) mbar_arrive(BAR(B_EMPTY + 6 + lane));
                PROFC(20);
#pragma unroll
                for (int g = 0; g < 4; g++) {
                    h2b[16 + 2 * g] = hmul2(pack2_relu(ac[4 * g], ac[4 * g + 1]), pack2(ac[16 + 4 * g], ac[16 + 4 * g + 1]));
                    h2b[16 + 2 * g + 1] = hmul2(pack2_relu(ac[4 * g + 2], ac[4 * g + 3]), pack2(ac[16 + 4 * g + 2], ac[16 + 4 * g + 3]));
                    h2g[(fc / 8 + g) * 512] = h2b[16 + 2 * g]; h2g[(fc / 8 + g) * 512 + 32] = h2b[16 + 2 * g + 1];
                }
                warp_arrive(BAR(B_PUB + 8));
                asm volatile("barrier.cluster.wait.aligned;" ::: "memory");
                if (lane == 0 && !sc) {
                    uint32_t rb;
                    asm volatile("mapa.shared::cluster.u32 %0, %1, %2;" : "=r"(rb) : "r"(BAR(B_PEER)), "r"(kh ^ 1));
                    asm volatile("mbarrier.arrive.relaxed.cluster.shared::cluster.b64 _, [%0];" ::"r"(rb) : "memory");
                }
            } else reg_def<8>(h2b + 16);
        }
        PROFC(21);
        if (RUN(7)) {
            float ac[56];
            reg_def<56>(ac);
            constexpr uint64_t DAN = dconst(2048, 128, 0);
            constexpr uint64_t DW = dconst(128, 512, 0);
            const uint32_t bx = mkdesc(sb, DW);
#pragma unroll
            for (int e = 0; e < 4; e++) {
                WAIT(B_FULL + e, 0);
                const uint64_t bd = ((DW & ~0xFFFFFFFFull) | bx) + (slot_off(e) >> 4);
                const uint32_t* hh = e < 2 ? h2a + 16 * e : h2b + 16 * (e - 2);
                WG_FENCE();
#pragma unroll
                for (int k = 0; k < (e < 3 ? 4 : 2); k++) wgmma_rl_112(ac, hh[4 * k], hh[4 * k + 1], hh[4 * k + 2], hh[4 * k + 3], bd + (k >> 1) * 512 + (k & 1) * 16, (e | k) != 0);
                WG_COMMIT();
                if (e > 0) { WG_WAIT(1); warp_arrive(BAR(B_EMPTY + e - 1)); }
            }
            PROFC(22);
            uint32_t ad = mkdesc(sb + 4 * 16384 + 8192 + w * 1024, DAN), bd = bx + 4 * 1024, fb_ = BAR(B_FULL + 4), eb_ = BAR(B_EMPTY + 3), par = sc;
#pragma unroll 1
            for (int e = 4; e < 25; e++) {
                mbar_wait_c(fb_, par);
                WG_FENCE();
                wgmma_ss_112<DAN, DW>(ac, ad, bd, 1);
                wgmma_ss_112<DAN, DW>(ac, ad + 256, bd + 16, 1);
                WG_COMMIT();
                WG_WAIT(1);
                warp_arrive(eb_);
                eb_ = fb_ + 8 * (B_EMPTY - B_FULL);
                ad += 1024; bd += 1024; fb_ += 8;
                if (e == 11 || e == 23) { ad -= 12 * 1024; bd -= 12 * 1024; fb_ -= 96; par = (par ^ 1) | sc; }
            }
            mbar_wait_cluster(BAR(B_PEER), sc);
            WG_WAIT(0);
            reg_fence<56>(ac);
            PROFC(24);
            uint32_t rdst, rbar;
            asm volatile("mapa.shared::cluster.u32 %0, %1, %2;" : "=r"(rdst) : "r"(sb + OFF_Y + (5 + w) * 16384 + t * 16), "r"(kh ^ 1 ^ sc));
            asm volatile("mapa.shared::cluster.u32 %0, %1, %2;" : "=r"(rbar) : "r"(BAR(B_XCH + w)), "r"(kh ^ 1 ^ sc));
#pragma unroll
            for (int g = 0; g < 7; g++) {
                const float v0 = ac[28 + 4 * g + 0], v1 = ac[28 + 4 * g + 1];
                const float v2 = ac[28 + 4 * g + 2], v3 = ac[28 + 4 * g + 3];
                if (!sc) asm volatile("st.async.shared::cluster.mbarrier::complete_tx::bytes.v4.f32 [%0], {%1,%2,%3,%4}, [%5];"
                             ::"r"(rdst + g * 2048), "f"(v0), "f"(v1), "f"(v2), "f"(v3), "r"(rbar) : "memory");
            }
            mbar_wait_cluster(BAR(B_XCH + w), sc);
            PROFC(25);
            uint32_t op[16];
#pragma unroll
            for (int g = 0; g < 7; g++) {
                const uint4 rv = *(const uint4*)(smem + OFF_Y + (5 + w) * 16384 + t * 16 + g * 2048);
                const float2 gb = *(const float2*)(smem + M_G + 224 + (8 * g + 2 * q) * 4);
                const float v0 = ac[4 * g + 0] + __uint_as_float(rv.x), v1 = ac[4 * g + 1] + __uint_as_float(rv.y);
                const float v2 = ac[4 * g + 2] + __uint_as_float(rv.z), v3 = ac[4 * g + 3] + __uint_as_float(rv.w);
                op[2 * g] = pack2(fmaf(gb.x, v0, bf_lo(x1p[2 * g])), fmaf(gb.y, v1, bf_hi(x1p[2 * g])));
                op[2 * g + 1] = pack2(fmaf(gb.x, v2, bf_lo(x1p[2 * g + 1])), fmaf(gb.y, v3, bf_hi(x1p[2 * g + 1])));
            }
            WAIT(B_EMPTY + 1, 0);
            const uint32_t oc = sb + OUT_STAGE + warp * 1792;
            const uint32_t oa = oc + (((lane >> 3) & 1) * 8 + (lane & 7)) * 112 + (lane >> 4) * 16;
            stsm4(oa, op[0], op[1], op[2], op[3]); stsm4(oa + 32, op[4], op[5], op[6], op[7]); stsm4(oa + 64, op[8], op[9], op[10], op[11]);
            asm volatile("stmatrix.sync.aligned.m8n8.x2.shared.b16 [%0], {%1,%2};" ::"r"(oa + 96), "r"(op[12]), "r"(op[13]));
            fence_async_smem();
            __syncwarp();
            asm volatile("{\n.reg .pred p;\nelect.sync _|p, 0xffffffff;\n@p cp.async.bulk.tensor.3d.global.shared::cta.bulk_group [%0, {%2, %3, %4}], [%1];\n"
                         "cp.async.bulk.commit_group;\ncp.async.bulk.wait_group.read 0;\n}" ::"l"(&p.om), "r"(oc), "r"(56 * j), "r"(128 * r + 16 * warp), "r"(0) : "memory");
        }
        PROFC(26);
        bar_sync(1 + w, 128);
        if (wi == 0) warp_arrive(BAR(B_DONE));
        return;
    }
    helper_late(p, r, j, warp PROF_ARGS);
}

#undef act
typedef CUresult (*EncodeFn)(CUtensorMap*, CUtensorMapDataType, cuuint32_t, void*, const cuuint64_t*, const cuuint64_t*, const cuuint32_t*,
                             const cuuint32_t*, CUtensorMapInterleave, CUtensorMapSwizzle, CUtensorMapL2promotion, CUtensorMapFloatOOBfill);

static void make_map(EncodeFn fn, CUtensorMap* m, const void* ptr, uint64_t d0, uint64_t d1, uint64_t d2, uint64_t s1, uint64_t s2,
                     uint32_t b0, uint32_t b1, uint32_t b2, CUtensorMapSwizzle sw) {
    cuuint64_t dims[3] = {d0, d1, d2}, strides[2] = {s1, s2};
    cuuint32_t box[3] = {b0, b1, b2}, es[3] = {1, 1, 1};
    CUresult rc = fn(m, CU_TENSOR_MAP_DATA_TYPE_BFLOAT16, 3, (void*)ptr, dims, strides, box, es, CU_TENSOR_MAP_INTERLEAVE_NONE, sw,
                     CU_TENSOR_MAP_L2_PROMOTION_L2_128B, CU_TENSOR_MAP_FLOAT_OOB_FILL_NONE);
    (void)rc;
}

extern "C" void kernel_launch(void* const* d_in, const int* in_sizes, int n_in, void* d_out, int out_size) {
    (void)in_sizes; (void)n_in; (void)out_size;
    static EncodeFn fn = nullptr;
    static uint32_t* act_base = nullptr;
    if (!fn) {
        cudaDriverEntryPointQueryResult st;
        cudaGetDriverEntryPoint("cuTensorMapEncodeTiled", (void**)&fn, cudaEnableDefault, &st);
        void* a = nullptr;
        cudaGetSymbolAddress(&a, g_act);
        act_base = (uint32_t*)(((uintptr_t)a + 0xFFFFF) & ~(uintptr_t)0xFFFFF);
        cudaFuncSetAttribute(fused_block_kernel, cudaFuncAttributeMaxDynamicSharedMemorySize, SMEM_BYTES);
    }
    Params p;
    p.x = (const bf16*)d_in[0];
    const bf16* wqkv = (const bf16*)d_in[1];
    p.wqkv = wqkv;
    p.wop = (const bf16*)d_in[2];
    p.wg = (const bf16*)d_in[4];
    p.wu = (const bf16*)d_in[5];
    p.wd = (const bf16*)d_in[6];
    p.c = (const bf16*)d_in[7];
    p.wmod = (const bf16*)d_in[8];
    p.out = (bf16*)d_out;
    p.zero = 0;
    p.actb = act_base;
    make_map(fn, &p.wm, p.wmod, 2688, 448, 1, 5376, 5376 * 448, 16, 224, 1, CU_TENSOR_MAP_SWIZZLE_NONE);
    make_map(fn, &p.wm2, p.wmod, 2688, 448, 1, 5376, 5376 * 448, 32, 224, 1, CU_TENSOR_MAP_SWIZZLE_NONE);
    make_map(fn, &p.om, p.out, 448, 2048, 1, 896, 896 * 2048, 56, 16, 1, CU_TENSOR_MAP_SWIZZLE_NONE);
    make_map(fn, &p.xm, p.x, 448, 2048, 1, 896, 896 * 2048, 64, 128, 1, CU_TENSOR_MAP_SWIZZLE_128B);
    make_map(fn, &p.qkv, wqkv, 1344, 448, 1, 2688, 2688 * 448, 64, 224, 1, CU_TENSOR_MAP_SWIZZLE_128B);
    make_map(fn, &p.wo, p.wop, 448, 448, 1, 896, 896 * 448, 64, 224, 1, CU_TENSOR_MAP_SWIZZLE_128B);
    make_map(fn, &p.ga, p.wg, 64, 448, 28, 3584, 128, 64, 32, 2, CU_TENSOR_MAP_SWIZZLE_128B);
    make_map(fn, &p.ua, p.wu, 64, 448, 28, 3584, 128, 64, 32, 2, CU_TENSOR_MAP_SWIZZLE_128B);
    make_map(fn, &p.gb, p.wg, 64, 448, 28, 3584, 128, 64, 64, 1, CU_TENSOR_MAP_SWIZZLE_128B);
    make_map(fn, &p.ub, p.wu, 64, 448, 28, 3584, 128, 64, 64, 1, CU_TENSOR_MAP_SWIZZLE_128B);
    make_map(fn, &p.gc, p.wg, 32, 448, 56, 3584, 64, 32, 64, 1, CU_TENSOR_MAP_SWIZZLE_64B);
    make_map(fn, &p.uc, p.wu, 32, 448, 56, 3584, 64, 32, 64, 1, CU_TENSOR_MAP_SWIZZLE_64B);
    make_map(fn, &p.dn, p.wd, 8, 1792, 56, 896, 16, 8, 32, 7, CU_TENSOR_MAP_SWIZZLE_NONE);
    fused_block_kernel<<<GRID, 384, SMEM_BYTES>>>(p);
}
```

```cpp
#include <cuda_runtime.h>
#include <cuda_bf16.h>
#include <cuda.h>
#include <stdint.h>

typedef __nv_bfloat16 bf16;

template<uint64_t CA, uint64_t CB> __device__ __forceinline__ void wgmma_sk_160(float* d, uint32_t da, uint32_t db, int sd) {
  asm volatile("{\n.reg .pred p;\n.reg .b64 a, b;\nsetp.ne.b32 p, %82, 0;\nmov.b64 a, {%80, %83};\nmov.b64 b, {%81, %84};\n"
    "wgmma.mma_async.sync.aligned.m64n160k16.f32.bf16.bf16 {%0,%1,%2,%3,%4,%5,%6,%7,%8,%9,%10,%11,%12,%13,%14,%15,%16,%17,%18,%19,%20,%21,%22,%23,%24,%25,%26,%27,%28,%29,%30,%31,%32,%33,%34,%35,%36,%37,%38,%39,%40,%41,%42,%43,%44,%45,%46,%47,%48,%49,%50,%51,%52,%53,%54,%55,%56,%57,%58,%59,%60,%61,%62,%63,%64,%65,%66,%67,%68,%69,%70,%71,%72,%73,%74,%75,%76,%77,%78,%79}, a, b, p, 1, 1, 0, 0;\n}\n"
    : "+f"(d[0]),"+f"(d[1]),"+f"(d[2]),"+f"(d[3]),"+f"(d[4]),"+f"(d[5]),"+f"(d[6]),"+f"(d[7]),"+f"(d[8]),"+f"(d[9]),"+f"(d[10]),"+f"(d[11]),"+f"(d[12]),"+f"(d[13]),"+f"(d[14]),"+f"(d[15]),"+f"(d[16]),"+f"(d[17]),"+f"(d[18]),"+f"(d[19]),"+f"(d[20]),"+f"(d[21]),"+f"(d[22]),"+f"(d[23]),"+f"(d[24]),"+f"(d[25]),"+f"(d[26]),"+f"(d[27]),"+f"(d[28]),"+f"(d[29]),"+f"(d[30]),"+f"(d[31]),"+f"(d[32]),"+f"(d[33]),"+f"(d[34]),"+f"(d[35]),"+f"(d[36]),"+f"(d[37]),"+f"(d[38]),"+f"(d[39]),"+f"(d[40]),"+f"(d[41]),"+f"(d[42]),"+f"(d[43]),"+f"(d[44]),"+f"(d[45]),"+f"(d[46]),"+f"(d[47]),"+f"(d[48]),"+f"(d[49]),"+f"(d[50]),"+f"(d[51]),"+f"(d[52]),"+f"(d[53]),"+f"(d[54]),"+f"(d[55]),"+f"(d[56]),"+f"(d[57]),"+f"(d[58]),"+f"(d[59]),"+f"(d[60]),"+f"(d[61]),"+f"(d[62]),"+f"(d[63]),"+f"(d[64]),"+f"(d[65]),"+f"(d[66]),"+f"(d[67]),"+f"(d[68]),"+f"(d[69]),"+f"(d[70]),"+f"(d[71]),"+f"(d[72]),"+f"(d[73]),"+f"(d[74]),"+f"(d[75]),"+f"(d[76]),"+f"(d[77]),"+f"(d[78]),"+f"(d[79])
    : "r"(da), "r"(db), "r"(sd), "n"((uint32_t)(CA >> 32)), "n"((uint32_t)(CB >> 32)));
}
__device__ __forceinline__ void wgmma_rl_56(float* d, uint32_t a0, uint32_t a1, uint32_t a2, uint32_t a3, uint64_t db, int sd) {
  asm volatile("{\n.reg .pred p;\nsetp.ne.b32 p, %33, 0;\n"
    "wgmma.mma_async.sync.aligned.m64n56k16.f32.bf16.bf16 {%0,%1,%2,%3,%4,%5,%6,%7,%8,%9,%10,%11,%12,%13,%14,%15,%16,%17,%18,%19,%20,%21,%22,%23,%24,%25,%26,%27}, {%28,%29,%30,%31}, %32, p, 1, 1, 1;\n}\n"
    : "+f"(d[0]),"+f"(d[1]),"+f"(d[2]),"+f"(d[3]),"+f"(d[4]),"+f"(d[5]),"+f"(d[6]),"+f"(d[7]),"+f"(d[8]),"+f"(d[9]),"+f"(d[10]),"+f"(d[11]),"+f"(d[12]),"+f"(d[13]),"+f"(d[14]),"+f"(d[15]),"+f"(d[16]),"+f"(d[17]),"+f"(d[18]),"+f"(d[19]),"+f"(d[20]),"+f"(d[21]),"+f"(d[22]),"+f"(d[23]),"+f"(d[24]),"+f"(d[25]),"+f"(d[26]),"+f"(d[27])
    : "r"(a0), "r"(a1), "r"(a2), "r"(a3), "l"(db), "r"(sd));
}
template<uint64_t CA, uint64_t CB> __device__ __forceinline__ void wgmma_ss_56(float* d, uint32_t da, uint32_t db, int sd) {
  asm volatile("{\n.reg .pred p;\n.reg .b64 a, b;\nsetp.ne.b32 p, %30, 0;\nmov.b64 a, {%28, %31};\nmov.b64 b, {%29, %32};\n"
    "wgmma.mma_async.sync.aligned.m64n56k16.f32.bf16.bf16 {%0,%1,%2,%3,%4,%5,%6,%7,%8,%9,%10,%11,%12,%13,%14,%15,%16,%17,%18,%19,%20,%21,%22,%23,%24,%25,%26,%27}, a, b, p, 1, 1, 0, 1;\n}\n"
    : "+f"(d[0]),"+f"(d[1]),"+f"(d[2]),"+f"(d[3]),"+f"(d[4]),"+f"(d[5]),"+f"(d[6]),"+f"(d[7]),"+f"(d[8]),"+f"(d[9]),"+f"(d[10]),"+f"(d[11]),"+f"(d[12]),"+f"(d[13]),"+f"(d[14]),"+f"(d[15]),"+f"(d[16]),"+f"(d[17]),"+f"(d[18]),"+f"(d[19]),"+f"(d[20]),"+f"(d[21]),"+f"(d[22]),"+f"(d[23]),"+f"(d[24]),"+f"(d[25]),"+f"(d[26]),"+f"(d[27])
    : "r"(da), "r"(db), "r"(sd), "n"((uint32_t)(CA >> 32)), "n"((uint32_t)(CB >> 32)));
}
__device__ __forceinline__ void wgmma_rl_256(float* d, uint32_t a0, uint32_t a1, uint32_t a2, uint32_t a3, uint64_t db, int sd) {
  asm volatile("{\n.reg .pred p;\nsetp.ne.b32 p, %133, 0;\n"
    "wgmma.mma_async.sync.aligned.m64n256k16.f32.bf16.bf16 {%0,%1,%2,%3,%4,%5,%6,%7,%8,%9,%10,%11,%12,%13,%14,%15,%16,%17,%18,%19,%20,%21,%22,%23,%24,%25,%26,%27,%28,%29,%30,%31,%32,%33,%34,%35,%36,%37,%38,%39,%40,%41,%42,%43,%44,%45,%46,%47,%48,%49,%50,%51,%52,%53,%54,%55,%56,%57,%58,%59,%60,%61,%62,%63,%64,%65,%66,%67,%68,%69,%70,%71,%72,%73,%74,%75,%76,%77,%78,%79,%80,%81,%82,%83,%84,%85,%86,%87,%88,%89,%90,%91,%92,%93,%94,%95,%96,%97,%98,%99,%100,%101,%102,%103,%104,%105,%106,%107,%108,%109,%110,%111,%112,%113,%114,%115,%116,%117,%118,%119,%120,%121,%122,%123,%124,%125,%126,%127}, {%128,%129,%130,%131}, %132, p, 1, 1, 1;\n}\n"
    : "+f"(d[0]),"+f"(d[1]),"+f"(d[2]),"+f"(d[3]),"+f"(d[4]),"+f"(d[5]),"+f"(d[6]),"+f"(d[7]),"+f"(d[8]),"+f"(d[9]),"+f"(d[10]),"+f"(d[11]),"+f"(d[12]),"+f"(d[13]),"+f"(d[14]),"+f"(d[15]),"+f"(d[16]),"+f"(d[17]),"+f"(d[18]),"+f"(d[19]),"+f"(d[20]),"+f"(d[21]),"+f"(d[22]),"+f"(d[23]),"+f"(d[24]),"+f"(d[25]),"+f"(d[26]),"+f"(d[27]),"+f"(d[28]),"+f"(d[29]),"+f"(d[30]),"+f"(d[31]),"+f"(d[32]),"+f"(d[33]),"+f"(d[34]),"+f"(d[35]),"+f"(d[36]),"+f"(d[37]),"+f"(d[38]),"+f"(d[39]),"+f"(d[40]),"+f"(d[41]),"+f"(d[42]),"+f"(d[43]),"+f"(d[44]),"+f"(d[45]),"+f"(d[46]),"+f"(d[47]),"+f"(d[48]),"+f"(d[49]),"+f"(d[50]),"+f"(d[51]),"+f"(d[52]),"+f"(d[53]),"+f"(d[54]),"+f"(d[55]),"+f"(d[56]),"+f"(d[57]),"+f"(d[58]),"+f"(d[59]),"+f"(d[60]),"+f"(d[61]),"+f"(d[62]),"+f"(d[63]),"+f"(d[64]),"+f"(d[65]),"+f"(d[66]),"+f"(d[67]),"+f"(d[68]),"+f"(d[69]),"+f"(d[70]),"+f"(d[71]),"+f"(d[72]),"+f"(d[73]),"+f"(d[74]),"+f"(d[75]),"+f"(d[76]),"+f"(d[77]),"+f"(d[78]),"+f"(d[79]),"+f"(d[80]),"+f"(d[81]),"+f"(d[82]),"+f"(d[83]),"+f"(d[84]),"+f"(d[85]),"+f"(d[86]),"+f"(d[87]),"+f"(d[88]),"+f"(d[89]),"+f"(d[90]),"+f"(d[91]),"+f"(d[92]),"+f"(d[93]),"+f"(d[94]),"+f"(d[95]),"+f"(d[96]),"+f"(d[97]),"+f"(d[98]),"+f"(d[99]),"+f"(d[100]),"+f"(d[101]),"+f"(d[102]),"+f"(d[103]),"+f"(d[104]),"+f"(d[105]),"+f"(d[106]),"+f"(d[107]),"+f"(d[108]),"+f"(d[109]),"+f"(d[110]),"+f"(d[111]),"+f"(d[112]),"+f"(d[113]),"+f"(d[114]),"+f"(d[115]),"+f"(d[116]),"+f"(d[117]),"+f"(d[118]),"+f"(d[119]),"+f"(d[120]),"+f"(d[121]),"+f"(d[122]),"+f"(d[123]),"+f"(d[124]),"+f"(d[125]),"+f"(d[126]),"+f"(d[127])
    : "r"(a0), "r"(a1), "r"(a2), "r"(a3), "l"(db), "r"(sd));
}
template<uint64_t CA, uint64_t CB> __device__ __forceinline__ void wgmma_ss_128(float* d, uint32_t da, uint32_t db, int sd) {
  asm volatile("{\n.reg .pred p;\n.reg .b64 a, b;\nsetp.ne.b32 p, %66, 0;\nmov.b64 a, {%64, %67};\nmov.b64 b, {%65, %68};\n"
    "wgmma.mma_async.sync.aligned.m64n128k16.f32.bf16.bf16 {%0,%1,%2,%3,%4,%5,%6,%7,%8,%9,%10,%11,%12,%13,%14,%15,%16,%17,%18,%19,%20,%21,%22,%23,%24,%25,%26,%27,%28,%29,%30,%31,%32,%33,%34,%35,%36,%37,%38,%39,%40,%41,%42,%43,%44,%45,%46,%47,%48,%49,%50,%51,%52,%53,%54,%55,%56,%57,%58,%59,%60,%61,%62,%63}, a, b, p, 1, 1, 0, 1;\n}\n"
    : "+f"(d[0]),"+f"(d[1]),"+f"(d[2]),"+f"(d[3]),"+f"(d[4]),"+f"(d[5]),"+f"(d[6]),"+f"(d[7]),"+f"(d[8]),"+f"(d[9]),"+f"(d[10]),"+f"(d[11]),"+f"(d[12]),"+f"(d[13]),"+f"(d[14]),"+f"(d[15]),"+f"(d[16]),"+f"(d[17]),"+f"(d[18]),"+f"(d[19]),"+f"(d[20]),"+f"(d[21]),"+f"(d[22]),"+f"(d[23]),"+f"(d[24]),"+f"(d[25]),"+f"(d[26]),"+f"(d[27]),"+f"(d[28]),"+f"(d[29]),"+f"(d[30]),"+f"(d[31]),"+f"(d[32]),"+f"(d[33]),"+f"(d[34]),"+f"(d[35]),"+f"(d[36]),"+f"(d[37]),"+f"(d[38]),"+f"(d[39]),"+f"(d[40]),"+f"(d[41]),"+f"(d[42]),"+f"(d[43]),"+f"(d[44]),"+f"(d[45]),"+f"(d[46]),"+f"(d[47]),"+f"(d[48]),"+f"(d[49]),"+f"(d[50]),"+f"(d[51]),"+f"(d[52]),"+f"(d[53]),"+f"(d[54]),"+f"(d[55]),"+f"(d[56]),"+f"(d[57]),"+f"(d[58]),"+f"(d[59]),"+f"(d[60]),"+f"(d[61]),"+f"(d[62]),"+f"(d[63])
    : "r"(da), "r"(db), "r"(sd), "n"((uint32_t)(CA >> 32)), "n"((uint32_t)(CB >> 32)));
}
template<uint64_t CA, uint64_t CB> __device__ __forceinline__ void wgmma_ss_64(float* d, uint32_t da, uint32_t db, int sd) {
  asm volatile("{\n.reg .pred p;\n.reg .b64 a, b;\nsetp.ne.b32 p, %34, 0;\nmov.b64 a, {%32, %35};\nmov.b64 b, {%33, %36};\n"
    "wgmma.mma_async.sync.aligned.m64n64k16.f32.bf16.bf16 {%0,%1,%2,%3,%4,%5,%6,%7,%8,%9,%10,%11,%12,%13,%14,%15,%16,%17,%18,%19,%20,%21,%22,%23,%24,%25,%26,%27,%28,%29,%30,%31}, a, b, p, 1, 1, 0, 1;\n}\n"
    : "+f"(d[0]),"+f"(d[1]),"+f"(d[2]),"+f"(d[3]),"+f"(d[4]),"+f"(d[5]),"+f"(d[6]),"+f"(d[7]),"+f"(d[8]),"+f"(d[9]),"+f"(d[10]),"+f"(d[11]),"+f"(d[12]),"+f"(d[13]),"+f"(d[14]),"+f"(d[15]),"+f"(d[16]),"+f"(d[17]),"+f"(d[18]),"+f"(d[19]),"+f"(d[20]),"+f"(d[21]),"+f"(d[22]),"+f"(d[23]),"+f"(d[24]),"+f"(d[25]),"+f"(d[26]),"+f"(d[27]),"+f"(d[28]),"+f"(d[29]),"+f"(d[30]),"+f"(d[31])
    : "r"(da), "r"(db), "r"(sd), "n"((uint32_t)(CA >> 32)), "n"((uint32_t)(CB >> 32)));
}
template<uint64_t CA, uint64_t CB> __device__ __forceinline__ void wgmma_ss_112(float* d, uint32_t da, uint32_t db, int sd) {
  asm volatile("{\n.reg .pred p;\n.reg .b64 a, b;\nsetp.ne.b32 p, %58, 0;\nmov.b64 a, {%56, %59};\nmov.b64 b, {%57, %60};\n"
    "wgmma.mma_async.sync.aligned.m64n112k16.f32.bf16.bf16 {%0,%1,%2,%3,%4,%5,%6,%7,%8,%9,%10,%11,%12,%13,%14,%15,%16,%17,%18,%19,%20,%21,%22,%23,%24,%25,%26,%27,%28,%29,%30,%31,%32,%33,%34,%35,%36,%37,%38,%39,%40,%41,%42,%43,%44,%45,%46,%47,%48,%49,%50,%51,%52,%53,%54,%55}, a, b, p, 1, 1, 0, 1;\n}\n"
    : "+f"(d[0]),"+f"(d[1]),"+f"(d[2]),"+f"(d[3]),"+f"(d[4]),"+f"(d[5]),"+f"(d[6]),"+f"(d[7]),"+f"(d[8]),"+f"(d[9]),"+f"(d[10]),"+f"(d[11]),"+f"(d[12]),"+f"(d[13]),"+f"(d[14]),"+f"(d[15]),"+f"(d[16]),"+f"(d[17]),"+f"(d[18]),"+f"(d[19]),"+f"(d[20]),"+f"(d[21]),"+f"(d[22]),"+f"(d[23]),"+f"(d[24]),"+f"(d[25]),"+f"(d[26]),"+f"(d[27]),"+f"(d[28]),"+f"(d[29]),"+f"(d[30]),"+f"(d[31]),"+f"(d[32]),"+f"(d[33]),"+f"(d[34]),"+f"(d[35]),"+f"(d[36]),"+f"(d[37]),"+f"(d[38]),"+f"(d[39]),"+f"(d[40]),"+f"(d[41]),"+f"(d[42]),"+f"(d[43]),"+f"(d[44]),"+f"(d[45]),"+f"(d[46]),"+f"(d[47]),"+f"(d[48]),"+f"(d[49]),"+f"(d[50]),"+f"(d[51]),"+f"(d[52]),"+f"(d[53]),"+f"(d[54]),"+f"(d[55])
    : "r"(da), "r"(db), "r"(sd), "n"((uint32_t)(CA >> 32)), "n"((uint32_t)(CB >> 32)));
}
__device__ __forceinline__ void wgmma_rl_112(float* d, uint32_t a0, uint32_t a1, uint32_t a2, uint32_t a3, uint64_t db, int sd) {
  asm volatile("{\n.reg .pred p;\nsetp.ne.b32 p, %61, 0;\n"
    "wgmma.mma_async.sync.aligned.m64n112k16.f32.bf16.bf16 {%0,%1,%2,%3,%4,%5,%6,%7,%8,%9,%10,%11,%12,%13,%14,%15,%16,%17,%18,%19,%20,%21,%22,%23,%24,%25,%26,%27,%28,%29,%30,%31,%32,%33,%34,%35,%36,%37,%38,%39,%40,%41,%42,%43,%44,%45,%46,%47,%48,%49,%50,%51,%52,%53,%54,%55}, {%56,%57,%58,%59}, %60, p, 1, 1, 1;\n}\n"
    : "+f"(d[0]),"+f"(d[1]),"+f"(d[2]),"+f"(d[3]),"+f"(d[4]),"+f"(d[5]),"+f"(d[6]),"+f"(d[7]),"+f"(d[8]),"+f"(d[9]),"+f"(d[10]),"+f"(d[11]),"+f"(d[12]),"+f"(d[13]),"+f"(d[14]),"+f"(d[15]),"+f"(d[16]),"+f"(d[17]),"+f"(d[18]),"+f"(d[19]),"+f"(d[20]),"+f"(d[21]),"+f"(d[22]),"+f"(d[23]),"+f"(d[24]),"+f"(d[25]),"+f"(d[26]),"+f"(d[27]),"+f"(d[28]),"+f"(d[29]),"+f"(d[30]),"+f"(d[31]),"+f"(d[32]),"+f"(d[33]),"+f"(d[34]),"+f"(d[35]),"+f"(d[36]),"+f"(d[37]),"+f"(d[38]),"+f"(d[39]),"+f"(d[40]),"+f"(d[41]),"+f"(d[42]),"+f"(d[43]),"+f"(d[44]),"+f"(d[45]),"+f"(d[46]),"+f"(d[47]),"+f"(d[48]),"+f"(d[49]),"+f"(d[50]),"+f"(d[51]),"+f"(d[52]),"+f"(d[53]),"+f"(d[54]),"+f"(d[55])
    : "r"(a0), "r"(a1), "r"(a2), "r"(a3), "l"(db), "r"(sd));
}

constexpr int DM = 448;
constexpr int NCTA = 128;
#define MAPPING 1
#define GRID 128
#define PINGPONG 0
#define WIN 6
#define WIN_END 25
#define UNR_B 1
#define UNR_C 1
constexpr int kB = UNR_B, kC = UNR_C;
#define LIKELY(x) __builtin_expect(!!(x), 1)
#define PACE 1
#define PACE_END 6
#define GEMV_AT 1
#define NPRE 14
#define ATT_OFF 0
#define ATT_WG 1
#define XFIRST 7
#define KDELAY 0
#define KEARLY 1
#define MAP_S 4
constexpr int SPIN_LIMIT = 1 << 22;

constexpr uint32_t OFF_X = 0, OFF_Y = 114688, OFF_MISC = 229376, SMEM_BYTES = 232448;
constexpr uint32_t Y_VR = 0, Y_K = 28672, Y_KOWN = 57344, Y_VOWN = 71680, Y_Q = 86016;
constexpr uint32_t HALF = 57344;
constexpr uint32_t X_STAT = 49152;
constexpr uint32_t OUT_STAGE = 16384;
constexpr uint32_t M_BAR = OFF_MISC;
constexpr uint32_t M_ST = OFF_MISC + 512;
constexpr uint32_t M_G = OFF_MISC + 2304;
constexpr uint32_t M_EPOCH = OFF_MISC + 3040;
enum { B_XFULL = 0, B_FULLK = 7, B_FULLV = 8, B_FULLQ, B_KRFULL, B_VRFULL, B_WOFULL, B_XCH, B_MOD1 = 15, B_FULL = 16, B_WMFULL = 30,
       B_EMPTY = 32, B_XFREE = B_EMPTY + 12, B_GEMV, B_PEER,
       B_PUB = 47,
       B_WMFREE = 56, B_HRDY, B_GFULL = B_HRDY + 3, B_DONE = 31, B_DUMMY = B_GEMV };

__device__ uint32_t g_ticket;
__device__ __align__(128) uint32_t g_mod[8 * 6 * DM];
__device__ __align__(128) uint32_t g_flag[144 * 128];
constexpr int RB_WORDS = 262144, RB_KV = 0, RB_O = 57344, RB_X1 = 86016, RB_H2 = 143360, RB_ST = 258048;
__device__ __align__(128) uint32_t g_act[18 * RB_WORDS];
__device__ __align__(128) uint32_t g_wd[56 * 4 * 1792];
#define PROFH(id)
#define PROFH1(id)
#define PROFC(id)

struct alignas(64) Params {
    CUtensorMap wm, wm2, om, xm, qkv, wo, ga, ua, gb, ub, gc, uc, dn;
    const bf16 *x, *c, *wqkv, *wmod, *wg, *wu, *wd, *wop;
    bf16* out;
    uint32_t* actb;
    uint32_t zero;
};

__device__ __forceinline__ void mbar_init(uint32_t bar, int cnt) { asm volatile("mbarrier.init.shared::cta.b64 [%0], %1;" ::"r"(bar), "r"(cnt) : "memory"); }
__device__ __forceinline__ void mbar_expect_tx(uint32_t bar, uint32_t bytes) { asm volatile("mbarrier.arrive.expect_tx.shared::cta.b64 _, [%0], %1;" ::"r"(bar), "r"(bytes) : "memory"); }
__device__ __forceinline__ void mbar_arrive(uint32_t bar) { asm volatile("mbarrier.arrive.shared::cta.b64 _, [%0];" ::"r"(bar) : "memory"); }
__device__ __forceinline__ void mbar_wait(uint32_t bar, uint32_t parity) {
    uint32_t ok; int n = 0;
    do {
        asm volatile("{\n.reg .pred p;\nmbarrier.try_wait.parity.shared::cta.b64 p, [%1], %2;\nselp.u32 %0, 1, 0, p;\n}" : "=r"(ok) : "r"(bar), "r"(parity) : "memory");
        if (++n > SPIN_LIMIT) __trap();
    } while (!ok);
}
__device__ __forceinline__ void mbar_wait_c(uint32_t bar, uint32_t parity) {
    asm volatile("{\n.reg .pred p;\nWL:\nmbarrier.try_wait.parity.shared::cta.b64 p, [%0], %1, 0x989680;\n@!p bra WL;\n}" ::"r"(bar), "r"(parity) : "memory");
}
__device__ __forceinline__ void mbar_wait_cluster(uint32_t bar, uint32_t parity) {
    asm volatile("{\n.reg .pred p;\nWL:\nmbarrier.try_wait.parity.acquire.cluster.shared::cta.b64 p, [%0], %1, 0x989680;\n@!p bra WL;\n}" ::"r"(bar), "r"(parity) : "memory");
}
__device__ __forceinline__ void warp_arrive(uint32_t bar) {
    __syncwarp();
    asm volatile("{\n.reg .pred p;\nelect.sync _|p, 0xffffffff;\n@p mbarrier.arrive.shared::cta.b64 _, [%0];\n}" ::"r"(bar) : "memory");
}
__device__ __forceinline__ int opaque(int v) { return __shfl_sync(~0u, v, 0); }
__device__ __forceinline__ int fresh_tid() { int v; asm volatile("mov.u32 %0, %%tid.x;" : "=r"(v)); return v; }
__device__ __forceinline__ void bar_sync(int id, int n) { asm volatile("bar.sync %0, %1;" ::"r"(id), "r"(n) : "memory"); }
__device__ __forceinline__ void bar_arrive(int id, int n) { asm volatile("bar.arrive %0, %1;" ::"r"(id), "r"(n) : "memory"); }
__device__ __forceinline__ void fence_async_smem() { asm volatile("fence.proxy.async.shared::cta;" ::: "memory"); }
__device__ __forceinline__ void fence_async_global() { asm volatile("fence.proxy.async.global;" ::: "memory"); }
__device__ __forceinline__ void fence_gpu() { asm volatile("fence.release.gpu;" ::: "memory"); }
__device__ __forceinline__ void tma3(uint32_t dst, const CUtensorMap* m, int c0, int c1, int c2, uint32_t bar) {
    asm volatile("cp.async.bulk.tensor.3d.shared::cluster.global.mbarrier::complete_tx::bytes [%0], [%1, {%3, %4, %5}], [%2];"
                 ::"r"(dst), "l"(m), "r"(bar), "r"(c0), "r"(c1), "r"(c2) : "memory");
}
__device__ __forceinline__ void bulk_load(uint32_t dst, const void* src, uint32_t bytes, uint32_t bar) {
    asm volatile("cp.async.bulk.shared::cluster.global.mbarrier::complete_tx::bytes [%0], [%1], %2, [%3];" ::"r"(dst), "l"(src), "r"(bytes), "r"(bar) : "memory");
}
__device__ __forceinline__ void expect_e(uint32_t bar, uint32_t bytes) {
    asm volatile("{\n.reg .pred p;\nelect.sync _|p, 0xffffffff;\n@p mbarrier.arrive.expect_tx.shared::cta.b64 _, [%0], %1;\n}" ::"r"(bar), "r"(bytes) : "memory");
}
__device__ __forceinline__ void tma3_e(uint32_t dst, const CUtensorMap* m, int c0, int c1, int c2, uint32_t bar) {
    asm volatile("{\n.reg .pred p;\nelect.sync _|p, 0xffffffff;\n@p cp.async.bulk.tensor.3d.shared::cluster.global.mbarrier::complete_tx::bytes [%0], [%1, {%3, %4, %5}], [%2];\n}"
                 ::"r"(dst), "l"(m), "r"(bar), "r"(c0), "r"(c1), "r"(c2) : "memory");
}
__device__ __forceinline__ void bulk_e(uint32_t dst, const void* src, uint32_t bytes, uint32_t bar) {
    asm volatile("{\n.reg .pred p;\nelect.sync _|p, 0xffffffff;\n@p cp.async.bulk.shared::cluster.global.mbarrier::complete_tx::bytes [%0], [%1], %2, [%3];\n}"
                 ::"r"(dst), "l"(src), "r"(bytes), "r"(bar) : "memory");
}
__device__ __forceinline__ void init_e(uint32_t bar, int cnt) {
    asm volatile("{\n.reg .pred p;\nelect.sync _|p, 0xffffffff;\n@p mbarrier.init.shared::cta.b64 [%0], %1;\n}" ::"r"(bar), "r"(cnt) : "memory");
}
__device__ __forceinline__ void l2_prefetch_e(const void* src, uint32_t bytes) {
    asm volatile("{\n.reg .pred p;\nelect.sync _|p, 0xffffffff;\n@p cp.async.bulk.prefetch.L2.global [%0], %1;\n}" ::"l"(src), "r"(bytes) : "memory");
}
__device__ __forceinline__ uint32_t ld_relaxed(const uint32_t* p) { uint32_t v; asm volatile("ld.relaxed.gpu.global.u32 %0, [%1];" : "=r"(v) : "l"(p) : "memory"); return v; }
__device__ __forceinline__ void st_relaxed(uint32_t* p, uint32_t v) { asm volatile("st.relaxed.gpu.global.u32 [%0], %1;" ::"l"(p), "r"(v) : "memory"); }
__device__ __forceinline__ uint4 ld_relaxed4(const uint4* p) { uint4 v; asm volatile("ld.relaxed.gpu.global.v4.u32 {%0,%1,%2,%3}, [%4];" : "=r"(v.x), "=r"(v.y), "=r"(v.z), "=r"(v.w) : "l"(p) : "memory"); return v; }
__device__ __forceinline__ void st_relaxed4(uint4* p, uint4 v) { asm volatile("st.relaxed.gpu.global.v4.u32 [%0], {%1,%2,%3,%4};" ::"l"(p), "r"(v.x), "r"(v.y), "r"(v.z), "r"(v.w) : "memory"); }
__device__ __forceinline__ uint4 ldg_nc4(const void* p) { uint4 v; asm volatile("ld.global.nc.L1::no_allocate.v4.u32 {%0,%1,%2,%3}, [%4];" : "=r"(v.x), "=r"(v.y), "=r"(v.z), "=r"(v.w) : "l"(p)); return v; }
__device__ __forceinline__ uint32_t ldg_nc(const void* p) { uint32_t v; asm volatile("ld.global.nc.u32 %0, [%1];" : "=r"(v) : "l"(p)); return v; }
__device__ __forceinline__ uint32_t ld_acquire(const uint32_t* p) { uint32_t v; asm volatile("ld.acquire.gpu.global.u32 %0, [%1];" : "=r"(v) : "l"(p) : "memory"); return v; }
__device__ __forceinline__ uint4 lds4(uint32_t a) { uint4 v; asm volatile("ld.shared.v4.u32 {%0,%1,%2,%3}, [%4];" : "=r"(v.x), "=r"(v.y), "=r"(v.z), "=r"(v.w) : "r"(a) : "memory"); return v; }
__device__ __forceinline__ float2 lds2f(uint32_t a) { float2 v; asm volatile("ld.shared.v2.f32 {%0,%1}, [%2];" : "=f"(v.x), "=f"(v.y) : "r"(a) : "memory"); return v; }
__device__ __forceinline__ uint32_t lds1(uint32_t a) { uint32_t v; asm volatile("ld.shared.u32 %0, [%1];" : "=r"(v) : "r"(a) : "memory"); return v; }
__device__ __forceinline__ void sts4(uint32_t a, uint4 v) { asm volatile("st.shared.v4.u32 [%0], {%1,%2,%3,%4};" ::"r"(a), "r"(v.x), "r"(v.y), "r"(v.z), "r"(v.w) : "memory"); }
__device__ __forceinline__ void sts2(uint32_t a, uint32_t x, uint32_t y) { asm volatile("st.shared.v2.u32 [%0], {%1,%2};" ::"r"(a), "r"(x), "r"(y) : "memory"); }
__device__ __forceinline__ void sts1(uint32_t a, uint32_t v) { asm volatile("st.shared.u32 [%0], %1;" ::"r"(a), "r"(v) : "memory"); }
__device__ __forceinline__ void stsm4(uint32_t a, uint32_t r0, uint32_t r1, uint32_t r2, uint32_t r3) {
    asm volatile("stmatrix.sync.aligned.m8n8.x4.shared.b16 [%0], {%1,%2,%3,%4};" ::"r"(a), "r"(r0), "r"(r1), "r"(r2), "r"(r3));
}
__device__ __forceinline__ uint32_t pack2(float lo, float hi) { uint32_t r; asm("cvt.rn.bf16x2.f32 %0, %1, %2;" : "=r"(r) : "f"(hi), "f"(lo)); return r; }
__device__ __forceinline__ uint32_t pack2_relu(float lo, float hi) { uint32_t r; asm("cvt.rn.relu.bf16x2.f32 %0, %1, %2;" : "=r"(r) : "f"(hi), "f"(lo)); return r; }
__device__ __forceinline__ uint32_t hfma2(uint32_t a, uint32_t b, uint32_t c) { uint32_t r; asm("fma.rn.bf16x2 %0, %1, %2, %3;" : "=r"(r) : "r"(a), "r"(b), "r"(c)); return r; }
__device__ __forceinline__ uint32_t hmul2(uint32_t a, uint32_t b) { uint32_t r; asm("mul.rn.bf16x2 %0, %1, %2;" : "=r"(r) : "r"(a), "r"(b)); return r; }
__device__ __forceinline__ float bf_lo(uint32_t v) { return __uint_as_float(v << 16); }
__device__ __forceinline__ float bf_hi(uint32_t v) { return __uint_as_float(v & 0xFFFF0000u); }
__device__ __forceinline__ float bf_round(float v) { return bf_lo(pack2(v, 0.f)); }
__device__ __forceinline__ float ex2(float x) { float r; asm("ex2.approx.ftz.f32 %0, %1;" : "=f"(r) : "f"(x)); return r; }
__device__ __forceinline__ void mma16816(float* d, uint32_t a0, uint32_t a1, uint32_t a2, uint32_t a3, uint32_t b0, uint32_t b1) {
    asm("mma.sync.aligned.m16n8k16.row.col.f32.bf16.bf16.f32 {%0,%1,%2,%3}, {%4,%5,%6,%7}, {%8,%9}, {%0,%1,%2,%3};"
        : "+f"(d[0]), "+f"(d[1]), "+f"(d[2]), "+f"(d[3]) : "r"(a0), "r"(a1), "r"(a2), "r"(a3), "r"(b0), "r"(b1));
}
__device__ __forceinline__ void mma16816_first(float* d, uint32_t a0, uint32_t a1, uint32_t a2, uint32_t a3, uint32_t b0, uint32_t b1) {
    asm volatile("mma.sync.aligned.m16n8k16.row.col.f32.bf16.bf16.f32 {%0,%1,%2,%3}, {%4,%5,%6,%7}, {%8,%9}, {%10,%10,%10,%10};"
        : "=f"(d[0]), "=f"(d[1]), "=f"(d[2]), "=f"(d[3]) : "r"(a0), "r"(a1), "r"(a2), "r"(a3), "r"(b0), "r"(b1), "f"(0.f));
}
__device__ __forceinline__ void mma16816_v(float* d, uint32_t a0, uint32_t a1, uint32_t a2, uint32_t a3, uint32_t b0, uint32_t b1) {
    asm volatile("mma.sync.aligned.m16n8k16.row.col.f32.bf16.bf16.f32 {%0,%1,%2,%3}, {%4,%5,%6,%7}, {%8,%9}, {%0,%1,%2,%3};"
        : "+f"(d[0]), "+f"(d[1]), "+f"(d[2]), "+f"(d[3]) : "r"(a0), "r"(a1), "r"(a2), "r"(a3), "r"(b0), "r"(b1));
}
__device__ __forceinline__ void mma1688(float* d, uint32_t a0, uint32_t a1, uint32_t b0) {
    asm("mma.sync.aligned.m16n8k8.row.col.f32.bf16.bf16.f32 {%0,%1,%2,%3}, {%4,%5}, {%6}, {%0,%1,%2,%3};"
        : "+f"(d[0]), "+f"(d[1]), "+f"(d[2]), "+f"(d[3]) : "r"(a0), "r"(a1), "r"(b0));
}
__device__ __forceinline__ void ldsm4(uint32_t a, uint32_t* r) {
    asm volatile("ldmatrix.sync.aligned.m8n8.x4.shared.b16 {%0,%1,%2,%3}, [%4];" : "=r"(r[0]), "=r"(r[1]), "=r"(r[2]), "=r"(r[3]) : "r"(a));
}
__device__ __forceinline__ void ldsm4t(uint32_t a, uint32_t* r) {
    asm volatile("ldmatrix.sync.aligned.m8n8.x4.trans.shared.b16 {%0,%1,%2,%3}, [%4];" : "=r"(r[0]), "=r"(r[1]), "=r"(r[2]), "=r"(r[3]) : "r"(a));
}
__device__ __forceinline__ uint32_t nz(uint32_t v) { uint32_t r; asm("max.u32 %0, %1, 1;" : "=r"(r) : "r"(v)); return r; }
__device__ __forceinline__ float rcp(float x) { float r; asm("rcp.approx.ftz.f32 %0, %1;" : "=f"(r) : "f"(x)); return r; }
__device__ __forceinline__ uint2 ld_relaxed2(const void* p) { uint2 v; asm volatile("ld.relaxed.gpu.global.v2.u32 {%0,%1}, [%2];" : "=r"(v.x), "=r"(v.y) : "l"(p) : "memory"); return v; }
__device__ __forceinline__ void st_relaxed2(void* p, uint32_t x, uint32_t y) { asm volatile("st.relaxed.gpu.global.v2.u32 [%0], {%1,%2};" ::"l"(p), "r"(max(x, 1u)), "r"(max(y, 1u)) : "memory"); }
__host__ __device__ constexpr uint64_t dconst(uint32_t lbo, uint32_t sbo, uint32_t swz) {
    return ((uint64_t)(lbo >> 4) << 16) | ((uint64_t)(sbo >> 4) << 32) | ((uint64_t)swz << 62);
}
__device__ __forceinline__ uint32_t mkdesc(uint32_t addr, uint64_t c) { return (uint32_t)c | ((addr & 0x3FFFF) >> 4); }
#define WG_FENCE() asm volatile("wgmma.fence.sync.aligned;" ::: "memory")
#define WG_COMMIT() asm volatile("wgmma.commit_group.sync.aligned;" ::: "memory")
#define WG_WAIT(n) asm volatile("wgmma.wait_group.sync.aligned %0;" ::"n"(n) : "memory")
template <int N> __device__ __forceinline__ void reg_fence(float* d) {
#pragma unroll
    for (int i = 0; i < N; i++) asm volatile("" : "+f"(d[i])::"memory");
}
template <int N> __device__ __forceinline__ void reg_def(float* d) {
#pragma unroll
    for (int i = 0; i < N; i++) asm volatile("" : "=f"(d[i]));
}
template <int N> __device__ __forceinline__ void reg_def(uint32_t* d) {
#pragma unroll
    for (int i = 0; i < N; i++) asm volatile("" : "=r"(d[i]));
}
__device__ __forceinline__ bool is_unset(uint4 v) { return min(min(v.x, v.y), min(v.z, v.w)) == 0u; }
__device__ __forceinline__ uint4 nz4(uint32_t a, uint32_t b, uint32_t c, uint32_t d) { return make_uint4(max(a, 1u), max(b, 1u), max(c, 1u), max(d, 1u)); }
__device__ __forceinline__ void wait_flags(const uint32_t* p, uint32_t target, uint32_t mask) {
    int n = 0;
    while (~__ballot_sync(~0u, (int)(ld_relaxed(p) - target) >= 0) & mask) { if (++n > SPIN_LIMIT) __trap(); }
    asm volatile("fence.acquire.gpu;" ::: "memory");
}
__device__ __forceinline__ float silu_bf(uint32_t cbits) {
    const float c = __uint_as_float(cbits << 16);
    return bf_round(__fdividef(c, 1.f + fminf(ex2(-1.4426950408889634f * c), 1e30f)));
}
__device__ __forceinline__ void gemv_part(uint32_t wmbuf, int wp, int lane) {
    const uint32_t wa = wmbuf + wp * 512 + (8 * (lane >> 4) + (lane & 7)) * 32 + ((lane >> 3) & 1) * 16;
    float d[4] = {};
#pragma unroll
    for (int i = 0; i < 4; i++) {
        uint32_t A[4];
        const float2 v = lds2f(wmbuf + 28672 + (wp + 8 * i) * 32 + (lane & 3) * 8);
        ldsm4t(wa + (i < 3 || wp < 4 ? i : 0) * 4096, A);
        mma16816(d, A[0], A[1], A[2], A[3], __float_as_uint(v.x), __float_as_uint(v.y));
    }
    if ((lane & 3) == 0) {
        sts1(wmbuf + 29696 + (wp * 16 + (lane >> 2)) * 4, __float_as_uint(d[0]));
        sts1(wmbuf + 29696 + (wp * 16 + 8 + (lane >> 2)) * 4, __float_as_uint(d[2]));
    }
}
__device__ __forceinline__ uint32_t mod_word(float v, int col, uint32_t target) {
    v = bf_round(v);
    if ((col >= DM && col < 2 * DM) || (col >= 4 * DM && col < 5 * DM)) v += 1.f;
    return (pack2(v, 0.f) << 16) | (target & 0xFFFFu);
}
__device__ __forceinline__ const uint4* mod_src(int i, int r, int j, bool p2) {
    i = min(i, p2 ? 251 : 223);
    return (const uint4*)g_mod + (r & 7) * (6 * DM / 4) + (i < 224 ? (p2 ? 336 : 0) + i : (i < 238 ? 14 * j + i : 14 * j + i + 322));
}
__device__ __forceinline__ void mod_store(uint32_t sb, uint4 v, const uint4* src, int i) {
    const uint32_t tag = lds1(sb + M_EPOCH) + 1;
    while (__any_sync(~0u, (((v.x ^ tag) | (v.y ^ tag) | (v.z ^ tag) | (v.w ^ tag)) & 0xFFFFu) != 0u)) v = ld_relaxed4(src);
    if (i < 224) {
        const int isc = i >= 112, c4 = i - 112 * isc;
        const uint32_t a = sb + M_ST + (c4 >> 2) * 64 + (c4 & 1) * 32 + (c4 & 2) * 4 + (isc ? 0 : 4);
        sts1(a, __byte_perm(v.x, v.y, 0x7632));
        sts1(a + 16, __byte_perm(v.z, v.w, 0x7632));
    } else if (i < 252) {
        sts4(sb + M_G + (i - 224) * 16, make_uint4(v.x & 0xFFFF0000u, v.y & 0xFFFF0000u, v.z & 0xFFFF0000u, v.w & 0xFFFF0000u));
    }
}
__device__ __forceinline__ int pass_f(int fs, int ps) { return 224 * fs + ((fs & 1) ? (ps == 0 ? 96 : ps == 1 ? 32 : 0) : (ps == 0 ? 0 : ps == 1 ? 128 : 192)); }
__device__ __forceinline__ constexpr uint32_t slot_off(int l) { return l * 16384; }
__device__ __forceinline__ constexpr int g1_slot(int s) { return s % 7; }
__device__ __noinline__ void x1_fix(const uint32_t* g, uint32_t sa, int s) {
#pragma unroll 1
    for (int k = 4 * s; k < 4 * s + 4;) {
        const uint4 v = ld_relaxed4((const uint4*)(g + k * 256));
        sts4(sa + k * 1024, v);
        k += 2 * __all_sync(~0u, min(min(v.x, v.y), min(v.z, v.w)) != 0u);
    }
    __syncwarp();
}
__device__ __forceinline__ void ln_coeffs(float mean, float msq, uint32_t& r2, uint32_t& n2) {
    const float rs = bf_round(rsqrtf(fmaxf(msq - mean * mean, 0.f) + 1e-5f));
    r2 = pack2(rs, rs);
    n2 = pack2(-mean * rs, -mean * rs);
}

#define LOADW bulk_e(dst, g_wd + (size_t)((f >> 5) * 4 + nq) * 1792, 7168, bar);
template <int sec> __device__ __forceinline__ void ring_loader(const Params& p, uint32_t sb_, int r_, int j_, int lane) {
    const uint32_t sb = opaque(sb_);
    const int r = opaque(r_), j = opaque(j_), nq = j >> 1, fs = 4 * (j & 1) + nq;
    const int fa = pass_f(fs, 0), fb = pass_f(fs, 1), fc = pass_f(fs, 2);
    const uint32_t* h2src = (const uint32_t*)__shfl_sync(~0u, (unsigned long long)(p.actb + (size_t)r * RB_WORDS + RB_H2), 0);
    const CUtensorMap* gmap = (const CUtensorMap*)__shfl_sync(~0u, (unsigned long long)(&p.ga + sec), 0);
#define BAR(i) (sb + M_BAR + 8 * (i))
#define kh (j & 1)
            int sl = 0;
#pragma unroll 1
            for (int s = 0; s < 28; s++) {
                if (s == 7) { wait_flags(g_flag + (8 * r + j) * 128 + 96 + lane, lds1(sb + M_EPOCH) + 1, 0xFFFFu); fence_async_global(); }
                const int ps = s < 14 ? 0 : s < 21 ? 1 : 2;
                const uint32_t half = ps < 2 ? 8192 : 4096;
                const int sp = sl;
                if (s >= PACE && s < PACE_END) mbar_wait(BAR(B_FULL + s - PACE), 0);
                mbar_wait(BAR(B_EMPTY + sp), (s >= 7 && s < 14) || s >= 21);
                expect_e(BAR(B_FULL + sp), half);
                tma3_e(sb + slot_off(sp) + sec * half, gmap + 2 * ps, 0, ps ? 64 * sl : 32 * s, ps == 0 ? fa >> 6 : ps == 1 ? fb >> 6 : fc >> 5, BAR(B_FULL + sp));
                sl = sl == 6 ? 0 : sl + 1;
            }
            if (!sec) PROFH(3);
#pragma unroll 1
            for (int e = 0; e < 4; e++) {
                const uint32_t dst = sb + slot_off(e) + sec * 8192, bar = BAR(B_FULL + e);
                const int f = (e < 2 ? fa + 64 * e : e == 2 ? fb : fc) + 32 * sec;
                mbar_wait(BAR(B_EMPTY + e), 0);
                expect_e(bar, e == 3 && sec ? 0 : 7168);
                if (!(e == 3 && sec)) { LOADW }
            }
            sl = 4;
            int e = 4;
#pragma unroll 1
            for (int grp = 0; grp < 9; grp++) {
                const int ps = grp >= 6 ? 2 : grp >= 3 ? 1 : 0;
                int sidx = grp - 3 * ps;
                if (sec && sidx == 0) { mbar_wait(BAR(B_HRDY + ps), 0); fence_async_global(); }
                sidx += sidx >= nq;
                int f = pass_f(4 * kh + sidx, ps);
#pragma unroll 1
                for (int k = 4 >> ps; k > 0; k--, e++, f += 32) {
                    const uint32_t dst = sb + slot_off(sl), bar = BAR(B_FULL + sl);
                    mbar_wait(BAR(B_EMPTY + sl), e >= 12 && e < 24);
                    if (e < WIN_END && e >= WIN) mbar_wait(BAR(B_FULL + (sl >= WIN ? sl - WIN : sl + 12 - WIN)), e - WIN >= 12);
                    expect_e(bar, sec ? 8192 : 7168);
                    if (!sec) { LOADW }
                    else bulk_e(dst + 8192, h2src + f * 64, 8192, bar);
                    sl = sl == 11 ? 0 : sl + 1;
                }
            }
            if (!sec) PROFH(4);
}

#define PROF_PARAMS
#define PROF_ARGS
__device__ __noinline__ void helper_late(const Params& p, int r_, int j_, int warp_ PROF_PARAMS) {
    extern __shared__ __align__(1024) unsigned char smem[];
    const uint32_t sb = (uint32_t)__cvta_generic_to_shared(smem);
    const int r = opaque(r_), j = opaque(j_), warp = opaque(warp_), nq = j >> 1, b = 8 * r + j;
    uint32_t* const act = (uint32_t*)__shfl_sync(~0u, (unsigned long long)(p.actb + (size_t)r * RB_WORDS), 0);
    {
        const int lane = fresh_tid() & 31;
        const uint32_t target = lds1(sb + M_EPOCH) + 1;
        if (warp == 8) { expect_e(BAR(B_XCH), 14336); expect_e(BAR(B_XCH + 1), 14336); }
            if (warp == 9) {
#pragma unroll 1
                for (int kv = 0; kv < 2; kv++) {
                    mbar_wait(BAR(B_PUB + kv), 0);
                    wait_flags(g_flag + b * 128 + lane, target, (r >= 2 ? 6u : r == 1 ? 2u : 0u) << (8 * kv));
                    fence_async_global();
                    const uint32_t dst = sb + OFF_Y + (kv ? Y_VR : Y_K);
                    expect_e(BAR(B_KRFULL + kv), r >= 2 ? 28672 : r == 1 ? 14336 : 0);
                    if (r >= 2) bulk_e(dst, act - 2 * RB_WORDS + RB_KV + j * 7168 + kv * 3584, 14336, BAR(B_KRFULL + kv));
                    if (r >= 1) bulk_e(dst + 14336, act - RB_WORDS + RB_KV + j * 7168 + kv * 3584, 14336, BAR(B_KRFULL + kv));
                    if (kv == 0) { PROFH(8); }
                }
            } else if (warp == 8) {
                uint4 v[8];
                mbar_wait(BAR(B_WOFULL), 0);
#pragma unroll
                for (int k = 0; k < 8; k++) v[k] = ld_relaxed4(mod_src(lane + 32 * k, r, j, true));
#pragma unroll
                for (int k = 0; k < 8; k++) mod_store(sb, v[k], mod_src(lane + 32 * k, r, j, true), lane + 32 * k);
                warp_arrive(BAR(B_MOD1));
            } else if (warp == 11) {
                if (kh == 1 && r < 14) {
                    const uint32_t wmbuf = sb + OFF_X + HALF;
                    const int mcol = 2 * DM + 32 * (4 * r + nq);
                    mbar_wait(BAR(B_XFREE), 0);
                    tma3_e(wmbuf, &p.wm2, mcol, 0, 0, BAR(B_WMFULL));
                    tma3_e(wmbuf + 14336, &p.wm2, mcol, 224, 0, BAR(B_WMFULL));
#pragma unroll 1
                    for (int wd = lane; wd < 224; wd += 32) {
                        const uint32_t cb = __ldg((const uint32_t*)p.c + wd);
                        sts1(wmbuf + 28672 + (wd >> 3) * 32 + (wd & 3) * 8 + (wd & 4), pack2(silu_bf(cb & 0xFFFFu), silu_bf(cb >> 16)));
                    }
                    __syncwarp();
                    mbar_wait(BAR(B_WMFULL), 0);
                    const uint32_t wa = wmbuf + (8 * (lane >> 4) + (lane & 7)) * 64 + ((lane >> 3) & 1) * 16;
                    float d[2][4] = {};
#pragma unroll 4
                    for (int ks = 0; ks < 28; ks++) {
                        uint32_t A[8];
                        ldsm4t(wa + ks * 1024, A); ldsm4t(wa + ks * 1024 + 32, A + 4);
                        const float2 v = lds2f(wmbuf + 28672 + ks * 32 + (lane & 3) * 8);
                        mma16816(d[0], A[0], A[1], A[2], A[3], __float_as_uint(v.x), __float_as_uint(v.y));
                        mma16816(d[1], A[4], A[5], A[6], A[7], __float_as_uint(v.x), __float_as_uint(v.y));
                    }
                    const int q = lane & 3, col = mcol + 8 * q + (lane >> 2);
                    const uint32_t word = mod_word(q == 0 ? d[0][0] : q == 1 ? d[0][2] : q == 2 ? d[1][0] : d[1][2], col, target);
#pragma unroll
                    for (int i = 0; i < 8; i++) st_relaxed(g_mod + i * 6 * DM + col, word);
                }
                warp_arrive(BAR(B_WMFREE));
                mbar_wait(BAR(B_VRFULL), 0);
                l2_prefetch_e((const char*)p.wg + (size_t)b * 12544, 12544);
                l2_prefetch_e((const char*)p.wu + (size_t)b * 12544, 12544);
#pragma unroll 1
                for (int k = 0; k < (r < 12 ? 2 : 1); k++) {
                    const int u = 28 * kh + r + 16 * k;
                    expect_e(BAR(B_XFULL + k), 7168);
                    tma3_e(sb + OFF_Y + 102400, &p.dn, 0, 32 * u, 7 * j, BAR(B_XFULL + k));
                    tma3_e(sb + OFF_Y + 102400 + 3584, &p.dn, 0, 32 * u, 7 * (j ^ 1), BAR(B_XFULL + k));
                    mbar_wait(BAR(B_XFULL + k), 1);
                    asm volatile("{\n.reg .pred p;\nelect.sync _|p, 0xffffffff;\n@p cp.async.bulk.global.shared::cta.bulk_group [%0], [%1], 7168;\n"
                                 "cp.async.bulk.commit_group;\ncp.async.bulk.wait_group 0;\n}" ::"l"(g_wd + (size_t)(u * 4 + nq) * 1792), "r"(sb + OFF_Y + 102400) : "memory");
                    __syncwarp();
                }
                warp_arrive(BAR(B_FULLK));
                fence_gpu();
                if (lane < 16) st_relaxed(g_flag + (8 * lane + j) * 128 + 96 + r, target);
            }
        if (warp == 8 || warp == 11) {
            const int sec = warp == 11;
            if (sec) ring_loader<1>(p, sb, r, j, lane); else ring_loader<0>(p, sb, r, j, lane);
            mbar_wait(BAR(B_DONE), 0);
        } else if (warp == 9) {
#pragma unroll
            for (int ev = 0; ev < 4; ev++) { expect_e(BAR(B_GFULL + ev), ev < 2 ? HALF / 2 : 16384 + 4096); expect_e(BAR(B_XFULL + 2 + ev), ev < 2 ? HALF / 2 : HALF - 16384); }
            mbar_wait(BAR(B_PUB + 2), 0);
            const uint32_t* fp = g_flag + b * 128 + 32 + lane;
            const int par = (target - 1) & 1;
#pragma unroll 1
            for (int n = 0, ev = 0; ev < 4; n++) {
                if (ev == 1) mbar_wait(BAR(B_PUB + 3), 0);
                uint32_t ok = __ballot_sync(~0u, (int)(ld_relaxed(fp) - target) >= 0) >> (8 * ev);
                while ((ok & 0xFFu) == 0xFFu) {
                    if (ev == 1) mbar_wait(BAR(B_FULLK), 1);
                    asm volatile("fence.acquire.gpu;" ::: "memory");
                    fence_async_global();
                    const int tile = (ev & 1) + (ev >> 1) * par * 2;
                    const uint32_t dst = sb + (ev == 0 ? OFF_X : OFF_Y + (ev & 1) * HALF), first = ev < 2 ? HALF / 2 : 16384;
                    const char* src = (const char*)(act + RB_O + ((ev >> 1) * 2 + tile) * 14336);
                    if (ev >= 2) bulk_e(sb + OFF_X + X_STAT + (ev & 1) * 49152, act + RB_ST + tile * 1024, 4096, BAR(B_GFULL + ev));
                    bulk_e(dst, src, first, BAR(B_GFULL + ev));
                    bulk_e(dst + first, src + first, HALF - first, BAR(B_XFULL + 2 + ev));
                    if (ev) PROFH(4 + ev);
                    ev++; ok >>= 8;
                }
                if (n > SPIN_LIMIT) __trap();
            }
            mbar_wait(BAR(B_XFULL + 5), 1);
#pragma unroll 1
            for (int hf = 0; hf < 2; hf++) {
                const int tile = (par ^ 1) * 2 + hf;
                uint4* xz = (uint4*)(act + RB_X1 + tile * 14336 + j * 1792) + lane;
#pragma unroll
                for (int i = 0; i < 14; i++) xz[i * 32] = make_uint4(0, 0, 0, 0);
                ((uint4*)(act + RB_ST + (tile * 8 + j) * 128))[lane] = make_uint4(0, 0, 0, 0);
            }
#pragma unroll 1
            for (int ps = 0; ps < 3; ps++) {
                mbar_wait(BAR(B_PUB + 6 + ps), 0);
                wait_flags(g_flag + b * 128 + 64 + lane, target, (0x55u << kh) << (8 * ps));
                warp_arrive(BAR(B_HRDY + ps));
                PROFH(9 + ps);
            }
        } else {
#pragma unroll 1
            for (int k = 0; k < 9; k++) {
                uint32_t* fp = k < 2 ? g_flag + (b + 8 * lane) * 128 + k * 8 + lane : g_flag + (8 * r + lane) * 128 + 16 + k * 8 + j;
                mbar_wait(BAR(B_PUB + k), 0);
                if (k != 4 && k != 5) fence_gpu();
                if (k < 2 ? (lane == 1 || lane == 2) : lane < 8) st_relaxed(fp, target);
                if (k >= 3 && k <= 5) PROFH(k - 3);
            }
        }
    }
}

__global__ void __cluster_dims__(2, 1, 1) __launch_bounds__(384, 1) fused_block_kernel(const __grid_constant__ Params p) {
    extern __shared__ __align__(1024) unsigned char smem[];
    const uint32_t sb = (uint32_t)__cvta_generic_to_shared(smem);
    const int tid = threadIdx.x, lane = tid & 31, warp = __shfl_sync(~0u, tid >> 5, 0);
    const int m = blockIdx.x >> 1;
    int r, nq;
    if (m < 4) { r = 15; nq = m; }
    else if (m < 36) { r = (m - 4) & 7; nq = (m - 4) >> 3; }
    else { nq = (m - 36) / 7; r = m - 28 - 7 * nq; }
    const int j = opaque(2 * nq + (blockIdx.x & 1)), b = 8 * r + j, fs = 4 * kh + nq;
#define act (p.actb + (size_t)r * RB_WORDS)
    constexpr uint32_t sc = 0;
    if (lane == 0 && warp < 9 && warp != 6 && warp != 7) {
        const int i0 = warp == 8 ? 0 : 8 + 8 * warp, cnt = warp == 0 || warp == 8 ? 1 : warp < 3 ? 2 : 8;
#pragma unroll
        for (int k = 0; k < 8; k++) if (i0 + k != B_WMFULL) mbar_init(BAR(i0 + k), cnt);
        if (warp == 8) mbar_init(BAR(B_WMFULL), 1);
        asm volatile("fence.mbarrier_init.release.cluster;" ::: "memory");
        fence_async_smem();
    }

    if (warp >= 8) {
        const int lane = fresh_tid() & 31;
        const bool early = kh == 0, gemv = r < 14;
        const int mcol = early ? 16 * (4 * r + nq) : 2 * DM + 32 * (4 * r + nq);
        const uint32_t wmbuf = sb + OFF_Y + HALF;
        if (warp == 8) {
            __syncwarp();
            expect_e(BAR(B_WMFULL), gemv ? 28672 >> early : 0);
            if (early && gemv) { tma3_e(wmbuf, &p.wm, mcol, 0, 0, BAR(B_WMFULL)); tma3_e(wmbuf + 7168, &p.wm, mcol, 224, 0, BAR(B_WMFULL)); }
#pragma unroll
            for (int kb = 0; kb < XFIRST; kb++) {
                expect_e(BAR(B_XFULL + kb), 16384);
                tma3_e(sb + OFF_X + kb * 16384, &p.xm, 64 * kb, 128 * r, 0, BAR(B_XFULL + kb));
            }
        }
        asm volatile("setmaxnreg.dec.sync.aligned.u32 56;");
        if (warp == 9) {
#pragma unroll
            for (int i = 56; i < 64; i++) init_e(BAR(i), 1);
            fence_async_smem();
        }
        bar_arrive(0, 384);
        asm volatile("barrier.cluster.arrive.relaxed.aligned;" ::: "memory");
        if (warp == 8) {
#pragma unroll
            for (int kb = XFIRST; kb < 7; kb++) {
                expect_e(BAR(B_XFULL + kb), 16384);
                tma3_e(sb + OFF_X + kb * 16384, &p.xm, 64 * kb, 128 * r, 0, BAR(B_XFULL + kb));
            }
            if (KDELAY >= 0) { mbar_wait(BAR(B_XFULL + KDELAY), 0); l2_prefetch_e((const char*)p.wqkv + (size_t)b * 9408, 9408); }
#pragma unroll 1
            for (int mt = 0; mt < 4; mt++) {
                if (mt == 1) bar_sync(9, 384);
                if (mt == 3) mbar_wait(BAR(B_WMFREE), 0);
                if (mt) mbar_wait(BAR(mt == 1 ? B_MOD1 : mt == 2 ? B_XFREE : B_VRFULL), 0);
                const uint32_t bar = BAR(mt == 3 ? B_WOFULL : B_FULLK + mt), dst = sb + (mt < 2 ? OFF_Y : OFF_X) + (mt & 1) * HALF;
                const int c0 = (mt < 2 ? DM + DM * mt : 0) + 56 * j - 8 * kh;
                if (!sc) {
                    expect_e(bar, HALF);
                    tma3_e(dst, mt == 3 ? &p.wo : &p.qkv, c0, 0, 0, bar);
                    tma3_e(dst + HALF / 2, mt == 3 ? &p.wo : &p.qkv, c0, 224, 0, bar);
                }
            }
        } else {
            if (KDELAY < 0 && warp == 10) l2_prefetch_e((const char*)p.wqkv + (size_t)b * 9408, 9408);
            bar_sync(9, 384);
            if (sc) return;
            if (warp == 11 && early) {
                const uint32_t target = lds1(sb + M_EPOCH) + 1;
                mbar_wait(BAR(B_GEMV), 0);
                float sum = 0.f;
#pragma unroll
                for (int i = 0; i < 8; i++) sum += *(const float*)(smem + OFF_Y + HALF + 29696 + (i * 16 + (lane & 15)) * 4);
                uint32_t* mg = g_mod + mcol + (lane & 15) + (lane >> 4) * 4 * 6 * DM;
                const uint32_t word = mod_word(sum, mcol, target);
                if (gemv) { st_relaxed(mg, word); st_relaxed(mg + 6 * DM, word); st_relaxed(mg + 12 * DM, word); st_relaxed(mg + 18 * DM, word); }
            }
        }
    }
    if (LIKELY(warp < 8)) {
        const int w = warp >> 2, wi = warp & 3;
#define COORDS const int t = fresh_tid() & 127, lane = t & 31, q = lane & 3, lr = lane >> 2, ra = 64 * w + 16 * wi + lr; \
        const uint32_t lx = (lane >> 4) ^ (lane & 7), mrow = (64 * w + 16 * wi + ((lane >> 3) & 1) * 8 + (lane & 7)) * 128; \
        (void)q; (void)lr; (void)ra; (void)lx; (void)mrow;
        const int sid = 2 * (j & 3) + w;
#define RUN(k) (!sc || sid == (k))
#define WAIT(i, par) mbar_wait_c(BAR(i), (par) | sc)
        constexpr uint64_t DB128 = dconst(4096, 1024, 1);
        {
            const int wd = fresh_tid();
            const uint32_t cb = wd < 224 ? __ldg((const uint32_t*)p.c + wd) : 0u;
            if (wd == 255 && !sc) sts1(sb + M_EPOCH, atomicAdd(&g_ticket, 1u) / NCTA);
            sts1(sb + OFF_Y + HALF + 28672 + (wd >> 3) * 32 + (wd & 3) * 8 + (wd & 4), pack2(silu_bf(cb & 0xFFFFu), silu_bf(cb >> 16)));
        }
        bar_arrive(9, 384);
        bar_sync(0, 384);
        asm volatile("barrier.cluster.arrive.relaxed.aligned;" ::: "memory");
        asm volatile("setmaxnreg.inc.sync.aligned.u32 224;");
        PROFC(0);
        uint32_t xr[16];
        {
            COORDS
            uint32_t h[112];
            uint32_t ra2, na2, rb2, nb2;
            const int mi = min(128 * w + t, 223);
            const uint4* msrc = mod_src(mi, r, j, false);
            uint4 mv;
            {
                float ds[4] = {}, da[2][4] = {}, db[2][4] = {};
                const uint32_t ONE2 = 0x3F803F80u;
#pragma unroll
                for (int kb = 0; kb < 7; kb++) {
                    if (kb == GEMV_AT && kh == 0) { WAIT(B_WMFULL, 0); gemv_part(sb + OFF_Y + HALF, warp, lane); warp_arrive(BAR(B_GEMV)); }
                    WAIT(B_XFULL + kb, 0);
#pragma unroll
                    for (int k4 = 0; k4 < 4; k4++) ldsm4(sb + OFF_X + mrow + kb * 16384 + (((2 * k4) ^ lx) << 4), h + 16 * kb + 4 * k4);
#pragma unroll
                    for (int k4 = 0; k4 < 4; k4++) {
                        const uint32_t* f = h + 16 * kb + 4 * k4;
                        mma16816(ds, f[0], f[1], f[2], f[3], ONE2, ONE2);
                        mma1688(da[0], f[0], f[1], f[0]); mma1688(db[0], f[0], f[1], f[1]);
                        mma1688(da[1], f[2], f[3], f[2]); mma1688(db[1], f[2], f[3], f[3]);
                    }
                }
#pragma unroll
                for (int i = 0; i < 4; i++) {
                    const int ch = 7 * j + 2 * i + (lane >> 4);
                    ldsm4(sb + OFF_X + mrow + (ch >> 3) * 16384 + (((ch ^ lane) & 7) << 4), xr + 4 * i);
                }
                mv = ld_relaxed4(msrc);
                warp_arrive(BAR(B_XFREE));
                float qa = (lr & 1) ? da[0][1] + da[1][1] : da[0][0] + da[1][0];
                float qb = (lr & 1) ? db[0][3] + db[1][3] : db[0][2] + db[1][2];
                const int src = (lane & ~3) | (lr >> 1);
                qa = __shfl_sync(~0u, qa, src);
                qb = __shfl_sync(~0u, qb, src);
                ln_coeffs(ds[0] * (1.f / DM), qa * (1.f / DM), ra2, na2);
                ln_coeffs(ds[2] * (1.f / DM), qb * (1.f / DM), rb2, nb2);
#pragma unroll
                for (int i = 0; i < 4 * NPRE; i += 2) { h[i] = hfma2(h[i], ra2, na2); h[i + 1] = hfma2(h[i + 1], rb2, nb2); }
            }
            PROFC(1);
            {
                float ak[28], av[28], aq[28];
                uint32_t kp[14], vp[14];
                const uint64_t bq0 = (DB128 & ~0xFFFFFFFFull) | (mkdesc(sb + OFF_X, DB128) + kh), bk0 = bq0 + (OFF_Y >> 4), bv0 = bk0 + (HALF >> 4);
                uint32_t* kvg = act + RB_KV + j * 7168 + (8 * w + 2 * wi) * 224 + lane;
                mod_store(sb, mv, msrc, mi);
                bar_sync(3, 256);
                if (warp == 0) warp_arrive(BAR(B_MOD1));
                WAIT(B_FULLK, 0);
                PROFC(2);
                reg_def<28>(ak);
#pragma unroll
                for (int g4 = 0; g4 < 4; g4++) {
#pragma unroll
                    for (int ks = 7 * g4; ks < 7 * g4 + 7; ks++) {
                        const uint4 st = *(const uint4*)(smem + M_ST + ks * 64 + q * 16);
                        if (ks >= NPRE) {
                            h[4 * ks] = hfma2(h[4 * ks], ra2, na2); h[4 * ks + 1] = hfma2(h[4 * ks + 1], rb2, nb2);
                            h[4 * ks + 2] = hfma2(h[4 * ks + 2], ra2, na2); h[4 * ks + 3] = hfma2(h[4 * ks + 3], rb2, nb2);
                        }
                        h[4 * ks] = hfma2(h[4 * ks], st.x, st.y); h[4 * ks + 1] = hfma2(h[4 * ks + 1], st.x, st.y);
                        h[4 * ks + 2] = hfma2(h[4 * ks + 2], st.z, st.w); h[4 * ks + 3] = hfma2(h[4 * ks + 3], st.z, st.w);
                    }
                    WG_FENCE();
#pragma unroll
                    for (int ks = 7 * g4; ks < 7 * g4 + 7; ks++) wgmma_rl_56(ak, h[4 * ks], h[4 * ks + 1], h[4 * ks + 2], h[4 * ks + 3], bk0 + ks * 128, ks != 0);
                }
                WG_COMMIT();
                PROFC(3);
                reg_def<28>(av);
                WG_WAIT(0);
                reg_fence<28>(ak);
#pragma unroll
                for (int g = 0; g < 7; g++) {
                    kp[2 * g] = pack2(ak[4 * g], ak[4 * g + 1]); kp[2 * g + 1] = pack2(ak[4 * g + 2], ak[4 * g + 3]);
                    kvg[g * 32] = kp[2 * g]; kvg[224 + g * 32] = kp[2 * g + 1];
                }
                warp_arrive(BAR(B_PUB));
                PROFC(4);
                if (KEARLY) WAIT(B_FULLV, 0);
                WG_FENCE();
#pragma unroll
                for (int ks = KEARLY ? 0 : 8; ks < 28; ks++) wgmma_rl_56(av, h[4 * ks], h[4 * ks + 1], h[4 * ks + 2], h[4 * ks + 3], bv0 + ks * 128, ks != 0);
                WG_COMMIT();
                WAIT(B_FULLQ, 0);
                reg_def<28>(aq);
                WG_FENCE();
#pragma unroll
                for (int ks = 0; ks < 8; ks++) wgmma_rl_56(aq, h[4 * ks], h[4 * ks + 1], h[4 * ks + 2], h[4 * ks + 3], bq0 + ks * 128, ks != 0);
                WG_COMMIT();
                WG_WAIT(1);
                reg_fence<28>(av);
#pragma unroll
                for (int g = 0; g < 7; g++) {
                    vp[2 * g] = pack2(av[4 * g], av[4 * g + 1]); vp[2 * g + 1] = pack2(av[4 * g + 2], av[4 * g + 3]);
                    kvg[3584 + g * 32] = vp[2 * g]; kvg[3584 + 224 + g * 32] = vp[2 * g + 1];
                }
                warp_arrive(BAR(B_PUB + 1));
                PROFC(5);
                WG_FENCE();
#pragma unroll
                for (int ks = 8; ks < 28; ks++) wgmma_rl_56(aq, h[4 * ks], h[4 * ks + 1], h[4 * ks + 2], h[4 * ks + 3], bq0 + ks * 128, 1);
                WG_COMMIT();
                WAIT(B_PUB + 1, 0);
                const uint32_t rg = 8 * w + 2 * wi + ((lane >> 3) & 1);
                const uint32_t ko = sb + OFF_Y + Y_KOWN + rg * 896 + (lane & 7) * 16, qo = sb + OFF_Y + Y_Q + rg * 1024 + (lane >> 4) * 128 + (lane & 7) * 16;
#pragma unroll
                for (int g = 0; g < 6; g += 2) {
                    stsm4(ko + (g + (lane >> 4)) * 128, kp[2 * g], kp[2 * g + 1], kp[2 * g + 2], kp[2 * g + 3]);
                    stsm4(ko + (Y_VOWN - Y_KOWN) + (g + (lane >> 4)) * 128, vp[2 * g], vp[2 * g + 1], vp[2 * g + 2], vp[2 * g + 3]);
                }
                stsm4(ko + (lane >> 4) * (Y_VOWN - Y_KOWN) + 6 * 128, kp[12], kp[13], vp[12], vp[13]);
                WG_WAIT(0);
                reg_fence<28>(aq);
                __syncwarp();
                if (lane < 3 && w == 1) mbar_arrive(BAR(B_EMPTY + lane));
                uint32_t qp[14];
#pragma unroll
                for (int i = 0; i < 14; i++) qp[i] = pack2(aq[2 * i], aq[2 * i + 1]);
                stsm4(qo, qp[0], qp[1], qp[2], qp[3]);
                stsm4(qo + 256, qp[4], qp[5], q < 2 ? qp[6] : 0u, q < 2 ? qp[7] : 0u);
                stsm4(qo + 512, q < 2 ? 0u : qp[6], q < 2 ? 0u : qp[7], qp[8], qp[9]);
                stsm4(qo + 768, qp[10], qp[11], qp[12], qp[13]);
                fence_async_smem();
                if (!sc) bar_sync(3, 256);
            }
        }
        PROFC(6);
        WAIT(B_KRFULL, 0);
        if (ATT_OFF && w == ATT_WG) { const uint32_t t0 = clock(); while (clock() - t0 < ATT_OFF) {} }
        PROFC(7);
        if (RUN(2)) {
#pragma unroll 1
            for (int hf = sc; hf < 2; hf++) {
                COORDS
                float s[160];
                const float CS = 0.18898223650461361f * 1.4426950408889634f;
                const float NEG = __int_as_float(0xFF800000);
                constexpr uint64_t DQ = dconst(128, 1024, 0), DK = dconst(128, 896, 0);
                {
                    const uint32_t qd = mkdesc(sb + OFF_Y + Y_Q + hf * 8192 + w * 512, DQ), kd = mkdesc(sb + OFF_Y + Y_K + hf * 8 * 896 + w * 384, DK);
                    reg_def<160>(s);
                    WG_FENCE();
                    wgmma_sk_160<DQ, DK>(s, qd, kd, 0);
                    wgmma_sk_160<DQ, DK>(s, qd + 16, kd + 16, 1);
                    wgmma_sk_160<DQ, DK>(s + 80, qd, kd + 20 * 56, 0);
                    wgmma_sk_160<DQ, DK>(s + 80, qd + 16, kd + 20 * 56 + 16, 1);
                    WG_COMMIT();
                    WG_WAIT(0);
                    reg_fence<160>(s);
                }
                if (r < 2) {
                    const int pmin = 4 - 2 * r - hf;
#pragma unroll
                    for (int p4 = 0; p4 < 4; p4++)
                        if (p4 < pmin) {
#pragma unroll
                            for (int i = 0; i < 32; i++) asm volatile("mov.b32 %0, 0xFF800000;" : "=f"(s[32 * p4 + i]));
                        }
                }
                const bool c0 = 2 * q > lr, c1 = 2 * q + 1 > lr;
#pragma unroll
                for (int pp = 0; pp < 4; pp++) {
                    const bool me = pp == wi;
                    float* e = s + 8 * pp;
                    if (me && !c0) { e[0] = NEG; e[6] = NEG; }
                    if (me && !c1) { e[1] = NEG; e[7] = NEG; }
                    if (me) { e[2] = NEG; e[3] = NEG; }
                    e = s + 8 * (pp + 16);
                    if (me && c0) { e[0] = NEG; e[6] = NEG; }
                    if (me && c1) { e[1] = NEG; e[7] = NEG; }
                    if (me) { e[4] = NEG; e[5] = NEG; }
                }
#pragma unroll
                for (int i = 0; i < 24; i++) s[i] = (i >> 3) < wi ? s[136 + i] : s[i];
                int i0 = 0x80000000, i1 = 0x80000000, i2 = 0x80000000, i3 = 0x80000000;
#pragma unroll
                for (int pp = 0; pp < 17; pp++) {
                    const float* e = s + 8 * pp;
                    i0 = __vimax3_s32(i0, __float_as_int(e[0]), __float_as_int(e[1])); i1 = __vimax3_s32(i1, __float_as_int(e[2]), __float_as_int(e[3]));
                    i2 = __vimax3_s32(i2, __float_as_int(e[4]), __float_as_int(e[5])); i3 = __vimax3_s32(i3, __float_as_int(e[6]), __float_as_int(e[7]));
                }
                i0 = max(i0, i2); i1 = max(i1, i3);
                i0 = max(i0, __shfl_xor_sync(~0u, i0, 1)); i1 = max(i1, __shfl_xor_sync(~0u, i1, 1));
                i0 = max(i0, __shfl_xor_sync(~0u, i0, 2)); i1 = max(i1, __shfl_xor_sync(~0u, i1, 2));
                float ma = __int_as_float(i0), mb = __int_as_float(i1);
                if (__any_sync(~0u, (i0 | i1) < 0)) {
                    ma = NEG; mb = NEG;
#pragma unroll
                    for (int i = 0; i < 136; i += 4) { ma = fmaxf(ma, fmaxf(s[i], s[i + 1])); mb = fmaxf(mb, fmaxf(s[i + 2], s[i + 3])); }
                    ma = fmaxf(ma, __shfl_xor_sync(~0u, ma, 1)); mb = fmaxf(mb, __shfl_xor_sync(~0u, mb, 1));
                    ma = fmaxf(ma, __shfl_xor_sync(~0u, ma, 2)); mb = fmaxf(mb, __shfl_xor_sync(~0u, mb, 2));
                }
                const float na = -ma * CS, nb = -mb * CS;
                PROFC(8 + 3 * hf);
                {
                    WAIT(B_VRFULL, 0);
                    float o[16] = {}, rs[4] = {};
                    const uint32_t va = sb + OFF_Y + Y_VR + (8 * hf + ((lane >> 3) & 1)) * 896 + (3 * w + (lane >> 4)) * 128 + (lane & 7) * 16;
                    constexpr uint32_t OWN = Y_VOWN - 32 * 896;
#pragma unroll
                    for (int pp = 0; pp < 17; pp++) {
                        uint32_t B[8];
                        const uint32_t v = va + pp * 1792 + (pp < 3 ? (pp < wi ? 17 * 1792 + OWN : 0) : pp == 16 ? OWN : pp >= 12 ? hf * OWN : 0);
                        ldsm4t(v, B); ldsm4t(v + 256, B + 4);
                        float e[8];
#pragma unroll
                        for (int i = 0; i < 8; i++) e[i] = ex2(fmaf(s[8 * pp + i], CS, (i & 2) ? nb : na));
                        const uint32_t p0 = pack2(e[0], e[1]), p1 = pack2(e[2], e[3]), p2 = pack2(e[4], e[5]), p3 = pack2(e[6], e[7]);
                        mma16816(rs, p0, p1, p2, p3, 0x3F803F80u, 0x3F803F80u);
#pragma unroll
                        for (int g = 0; g < 4; g++) mma16816(o + 4 * g, p0, p1, p2, p3, B[2 * g], B[2 * g + 1]);
                    }
                    PROFC(9 + 3 * hf);
                    const float ia = rcp(rs[0]), ib = rcp(rs[2]);
                    uint32_t* og = act + RB_O + hf * 14336 + (7 * j + 3 * w) * 256 + wi * 64 + lane;
#pragma unroll
                    for (int g = 0; g < 4; g++) {
                        if ((g == 3 - 3 * w) ? ((q >> 1) == w) : true) {
                            og[g * 256] = pack2(o[4 * g] * ia, o[4 * g + 1] * ia);
                            og[g * 256 + 32] = pack2(o[4 * g + 2] * ib, o[4 * g + 3] * ib);
                        }
                    }
                    warp_arrive(BAR(B_PUB + 2 + hf));
                    PROFC(10 + 3 * hf);
                }
            }
        }
        uint32_t x1p[14];
        COORDS
        constexpr uint64_t DT = dconst(1024, 128, 0);
        const int tile = opaque((lds1(sb + M_EPOCH) & 1) * 2 + w);
        if (RUN(4)) {
            float ac[28];
            const uint32_t ad = mkdesc(sb + (w ? OFF_Y + HALF : OFF_X), DT), bd = mkdesc(sb + OFF_X + HALF, DB128) + kh;
            WAIT(B_WOFULL, 0);
            WAIT(B_MOD1, 1);
            WAIT(B_GFULL + w, 0);
            PROFC(28);
            reg_def<28>(ac);
#pragma unroll 1
            for (int u = 0; u < 4; u++) {
                if (u == 2) WAIT(B_XFULL + 2 + w, 1);
                WG_FENCE();
#pragma unroll
                for (int i = 0; i < 7; i++) wgmma_ss_56<DT, DB128>(ac, ad + (7 * u + i) * 128, bd + (7 * u + i) * 128, (u | i) != 0);
            }
            WG_COMMIT();
            WG_WAIT(0);
            reg_fence<28>(ac);
            PROFC(14);
            __syncwarp();
            if (lane < 3) mbar_arrive(BAR(B_EMPTY + 4 - w + lane));
            if (lane < 3 && w == 0) mbar_arrive(BAR(B_EMPTY + lane));
            float ds[4] = {}, da[4] = {}, db[4] = {};
            uint32_t* xo = act + RB_X1 + tile * 14336 + 7 * j * 256 + wi * 64 + lane;
#pragma unroll
            for (int g = 0; g < 7; g++) {
                const float2 ga = *(const float2*)(smem + M_G + (8 * g + 2 * q) * 4);
                x1p[2 * g] = pack2(fmaf(ga.x, ac[4 * g], bf_lo(xr[2 * g])), fmaf(ga.y, ac[4 * g + 1], bf_hi(xr[2 * g])));
                x1p[2 * g + 1] = pack2(fmaf(ga.x, ac[4 * g + 2], bf_lo(xr[2 * g + 1])), fmaf(ga.y, ac[4 * g + 3], bf_hi(xr[2 * g + 1])));
                st_relaxed(xo + g * 256, nz(x1p[2 * g])); st_relaxed(xo + g * 256 + 32, nz(x1p[2 * g + 1]));
                mma1688(ds, x1p[2 * g], x1p[2 * g + 1], 0x3F803F80u);
                mma1688(da, x1p[2 * g], x1p[2 * g + 1], x1p[2 * g]);
                mma1688(db, x1p[2 * g], x1p[2 * g + 1], x1p[2 * g + 1]);
            }
            const int src = (lane & ~3) | (lr >> 1);
            const float qa = __shfl_sync(~0u, (lr & 1) ? da[1] : da[0], src), qb = __shfl_sync(~0u, (lr & 1) ? db[3] : db[2], src);
            const float kk = (q & 1) ? ((q & 2) ? qb : qa) : ((q & 2) ? ds[2] : ds[0]);
            st_relaxed(act + RB_ST + ((tile * 8 + j) * 64 + 16 * wi + lr + 4 * (q & 2)) * 2 + (q & 1), nz(__float_as_uint(kk)));
            __syncwarp();
            if (lane < 2) mbar_arrive(BAR(B_PUB + 4 + w));
        } else reg_def<14>(x1p);
        PROFC(15);
        uint32_t h2a[32], h2b[24];
        {
            const int fa = pass_f(fs, 0), fb = pass_f(fs, 1), fc = pass_f(fs, 2);
            uint32_t* h2g = act + RB_H2 + (8 * w + 2 * wi) * 32 + lane;
            const uint32_t a0 = mkdesc(sb + OFF_Y + w * HALF, DT);
            if (RUN(3)) {
                uint32_t ra2, na2, rb2, nb2;
                {
                    const uint32_t* sg = act + RB_ST + ((tile * 8 + 2 * q) * 64 + 16 * wi + lr) * 2;
                    uint2 u[4];
                    WAIT(B_GFULL + 2 + w, 0);
                    PROFC(16);
#pragma unroll
                    for (int i = 0; i < 4; i++) { const float2 v = lds2f(sb + OFF_X + X_STAT + w * 49152 + ((2 * q + (i >> 1)) * 64 + 16 * wi + lr + 8 * (i & 1)) * 8); u[i] = make_uint2(__float_as_uint(v.x), __float_as_uint(v.y)); }
                    while (__any_sync(~0u, min(min(min(u[0].x, u[0].y), min(u[1].x, u[1].y)), min(min(u[2].x, u[2].y), min(u[3].x, u[3].y))) < 1u - sc)) {
#pragma unroll
                        for (int i = 0; i < 4; i++) u[i] = ld_relaxed2(sg + (i >> 1) * 128 + (i & 1) * 16);
                    }
                    warp_arrive(BAR(B_EMPTY + 3 + 3 * w));
                    float v[4] = {__uint_as_float(u[0].x) + __uint_as_float(u[2].x), __uint_as_float(u[0].y) + __uint_as_float(u[2].y),
                                  __uint_as_float(u[1].x) + __uint_as_float(u[3].x), __uint_as_float(u[1].y) + __uint_as_float(u[3].y)};
#pragma unroll
                    for (int i = 0; i < 4; i++) { v[i] += __shfl_xor_sync(~0u, v[i], 1); v[i] += __shfl_xor_sync(~0u, v[i], 2); }
                    ln_coeffs(v[0] * (1.f / DM), v[1] * (1.f / DM), ra2, na2);
                    ln_coeffs(v[2] * (1.f / DM), v[3] * (1.f / DM), rb2, nb2);
                }
                const uint32_t ha = sb + OFF_Y + w * HALF + (lane >> 4) * 1024 + (2 * wi + ((lane >> 3) & 1)) * 128 + (lane & 7) * 16;
                const uint32_t sta = sb + M_ST + q * 16;
                const uint32_t* xg = act + RB_X1 + tile * 14336 + (lane >> 4) * 256 + wi * 64 + (lane & 15) * 4;
                uint32_t x[8];
                const uint32_t xs = sb + OFF_Y + w * HALF + (lane >> 4) * 1024 + wi * 256 + (lane & 15) * 16;
                uint4 st[2];
                auto load = [&](int s) {
                    if (s == 4) mbar_wait_c(BAR(B_XFULL + 4 + w), 1);
                    ldsm4(ha + s * 4096, x); ldsm4(ha + s * 4096 + 2048, x + 4);
                    st[0] = lds4(sta + s * 128); st[1] = lds4(sta + s * 128 + 64);
                };
                auto prep = [&](int s, uint32_t* f) {
                    if (__any_sync(~0u, min(min(min(x[0], x[1]), min(x[2], x[3])), min(min(x[4], x[5]), min(x[6], x[7]))) < 1u - sc)) {
                        WG_WAIT(0);
                        x1_fix(xg, xs, s);
                        ldsm4(ha + s * 4096, x); ldsm4(ha + s * 4096 + 2048, x + 4);
                    }
#pragma unroll
                    for (int i = 0; i < 2; i++) {
                        f[4 * i] = hfma2(hfma2(x[4 * i], ra2, na2), st[i].x, st[i].y); f[4 * i + 1] = hfma2(hfma2(x[4 * i + 1], rb2, nb2), st[i].x, st[i].y);
                        f[4 * i + 2] = hfma2(hfma2(x[4 * i + 2], ra2, na2), st[i].z, st[i].w); f[4 * i + 3] = hfma2(hfma2(x[4 * i + 3], rb2, nb2), st[i].z, st[i].w);
                    }
                    if (s < 13) load(s + 1);
                    stsm4(ha + s * 4096, f[0], f[1], f[2], f[3]); stsm4(ha + s * 4096 + 2048, f[4], f[5], f[6], f[7]);
                };
                float ac[128];
                uint32_t fr[3][8];
                uint64_t bd = (DB128 & ~0xFFFFFFFFull) | mkdesc(sb, DB128);
                reg_def<128>(ac);
                load(0);
                prep(0, fr[0]);
                PROFC(17);
#pragma unroll
                for (int s = 0; s < 14; s++) {
                    const uint32_t* f = fr[s % 3];
                    WAIT(B_FULL + g1_slot(s), s >= 7);
                    WG_FENCE();
                    wgmma_rl_256(ac, f[0], f[1], f[2], f[3], bd, s != 0);
                    wgmma_rl_256(ac, f[4], f[5], f[6], f[7], bd + 128, 1);
                    bd += s == 6 ? p.zero - 6 * 1024ull : 1024;
                    WG_COMMIT();
                    if (s < 13) prep(s + 1, fr[(s + 1) % 3]);
                    if (s > 0) { WG_WAIT(1); warp_arrive(BAR(B_EMPTY + g1_slot(s - 1))); }
                }
                fence_async_smem();
                PROFC(18);
                WG_WAIT(0);
                reg_fence<128>(ac);
                warp_arrive(BAR(B_EMPTY + 6));
#pragma unroll
                for (int g = 0; g < 16; g++) {
                    h2a[2 * g] = hmul2(pack2_relu(ac[4 * g], ac[4 * g + 1]), pack2(ac[64 + 4 * g], ac[64 + 4 * g + 1]));
                    h2a[2 * g + 1] = hmul2(pack2_relu(ac[4 * g + 2], ac[4 * g + 3]), pack2(ac[64 + 4 * g + 2], ac[64 + 4 * g + 3]));
                }
                bar_sync(1 + w, 128);
            } else reg_def<32>(h2a);
            PROFC(19);
            if (RUN(5)) {
                float ac[64];
                reg_def<64>(ac);
                const uint32_t bx = mkdesc(sb, dconst(8192, 1024, 1));
#pragma unroll kB
                for (int s = 0; s < 7; s++) {
                    WAIT(B_FULL + s, 0);
                    const uint32_t ad = a0 + s * 512, bd = bx + (slot_off(s) >> 4);
                    WG_FENCE();
#pragma unroll
                    for (int k = 0; k < 4; k++) wgmma_ss_128<DT, DB128>(ac, ad + k * 128, bd + k * 128, (s | k) != 0);
                    WG_COMMIT();
                    if (s == 1) {
#pragma unroll
                        for (int g = 0; g < 16; g++) { h2g[(fa / 8 + g) * 512] = h2a[2 * g]; h2g[(fa / 8 + g) * 512 + 32] = h2a[2 * g + 1]; }
                        warp_arrive(BAR(B_PUB + 6));
                    }
                    if (s > 0) { WG_WAIT(1); warp_arrive(BAR(B_EMPTY + s - 1)); }
                }
                WG_WAIT(0);
                reg_fence<64>(ac);
                warp_arrive(BAR(B_EMPTY + 6));
#pragma unroll
                for (int g = 0; g < 8; g++) {
                    h2b[2 * g] = hmul2(pack2_relu(ac[4 * g], ac[4 * g + 1]), pack2(ac[32 + 4 * g], ac[32 + 4 * g + 1]));
                    h2b[2 * g + 1] = hmul2(pack2_relu(ac[4 * g + 2], ac[4 * g + 3]), pack2(ac[32 + 4 * g + 2], ac[32 + 4 * g + 3]));
                }
            } else reg_def<16>(h2b);
            PROFC(27);
            if (RUN(6)) {
                float ac[32];
                reg_def<32>(ac);
                const uint32_t bx = mkdesc(sb, dconst(4096, 512, 2));
#pragma unroll kC
                for (int s = 0; s < 7; s++) {
                    WAIT(B_FULL + s, 1);
                    const uint32_t ad = a0 + s * 512, bd = bx + (slot_off(s) >> 4);
                    WG_FENCE();
#pragma unroll
                    for (int k = 0; k < 4; k++) wgmma_ss_64<DT, dconst(4096, 512, 2)>(ac, ad + k * 128, bd + k * 64, (s | k) != 0);
                    WG_COMMIT();
                    if (s == 1) {
#pragma unroll
                        for (int g = 0; g < 8; g++) { h2g[(fb / 8 + g) * 512] = h2b[2 * g]; h2g[(fb / 8 + g) * 512 + 32] = h2b[2 * g + 1]; }
                        warp_arrive(BAR(B_PUB + 7));
                    }
                    if (s > 0) { WG_WAIT(1); warp_arrive(BAR(B_EMPTY + s - 1)); }
                }
                WG_WAIT(0);
                reg_fence<32>(ac);
                __syncwarp();
                if (lane < 6) mbar_arrive(BAR(B_EMPTY + 6 + lane));
                PROFC(20);
#pragma unroll
                for (int g = 0; g < 4; g++) {
                    h2b[16 + 2 * g] = hmul2(pack2_relu(ac[4 * g], ac[4 * g + 1]), pack2(ac[16 + 4 * g], ac[16 + 4 * g + 1]));
                    h2b[16 + 2 * g + 1] = hmul2(pack2_relu(ac[4 * g + 2], ac[4 * g + 3]), pack2(ac[16 + 4 * g + 2], ac[16 + 4 * g + 3]));
                    h2g[(fc / 8 + g) * 512] = h2b[16 + 2 * g]; h2g[(fc / 8 + g) * 512 + 32] = h2b[16 + 2 * g + 1];
                }
                warp_arrive(BAR(B_PUB + 8));
                asm volatile("barrier.cluster.wait.aligned;" ::: "memory");
                if (lane == 0 && !sc) {
                    uint32_t rb;
                    asm volatile("mapa.shared::cluster.u32 %0, %1, %2;" : "=r"(rb) : "r"(BAR(B_PEER)), "r"(kh ^ 1));
                    asm volatile("mbarrier.arrive.relaxed.cluster.shared::cluster.b64 _, [%0];" ::"r"(rb) : "memory");
                }
            } else reg_def<8>(h2b + 16);
        }
        PROFC(21);
        if (RUN(7)) {
            float ac[56];
            reg_def<56>(ac);
            constexpr uint64_t DAN = dconst(2048, 128, 0);
            constexpr uint64_t DW = dconst(128, 512, 0);
            const uint32_t bx = mkdesc(sb, DW);
#pragma unroll
            for (int e = 0; e < 4; e++) {
                WAIT(B_FULL + e, 0);
                const uint64_t bd = ((DW & ~0xFFFFFFFFull) | bx) + (slot_off(e) >> 4);
                const uint32_t* hh = e < 2 ? h2a + 16 * e : h2b + 16 * (e - 2);
                WG_FENCE();
#pragma unroll
                for (int k = 0; k < (e < 3 ? 4 : 2); k++) wgmma_rl_112(ac, hh[4 * k], hh[4 * k + 1], hh[4 * k + 2], hh[4 * k + 3], bd + (k >> 1) * 512 + (k & 1) * 16, (e | k) != 0);
                WG_COMMIT();
                if (e > 0) { WG_WAIT(1); warp_arrive(BAR(B_EMPTY + e - 1)); }
            }
            PROFC(22);
            uint32_t ad = mkdesc(sb + 4 * 16384 + 8192 + w * 1024, DAN), bd = bx + 4 * 1024, fb_ = BAR(B_FULL + 4), eb_ = BAR(B_EMPTY + 3), par = sc;
#pragma unroll 1
            for (int e = 4; e < 25; e++) {
                mbar_wait_c(fb_, par);
                WG_FENCE();
                wgmma_ss_112<DAN, DW>(ac, ad, bd, 1);
                wgmma_ss_112<DAN, DW>(ac, ad + 256, bd + 16, 1);
                WG_COMMIT();
                WG_WAIT(1);
                warp_arrive(eb_);
                eb_ = fb_ + 8 * (B_EMPTY - B_FULL);
                ad += 1024; bd += 1024; fb_ += 8;
                if (e == 11 || e == 23) { ad -= 12 * 1024; bd -= 12 * 1024; fb_ -= 96; par = (par ^ 1) | sc; }
            }
            mbar_wait_cluster(BAR(B_PEER), sc);
            WG_WAIT(0);
            reg_fence<56>(ac);
            PROFC(24);
            uint32_t rdst, rbar;
            asm volatile("mapa.shared::cluster.u32 %0, %1, %2;" : "=r"(rdst) : "r"(sb + OFF_Y + (5 + w) * 16384 + t * 16), "r"(kh ^ 1 ^ sc));
            asm volatile("mapa.shared::cluster.u32 %0, %1, %2;" : "=r"(rbar) : "r"(BAR(B_XCH + w)), "r"(kh ^ 1 ^ sc));
#pragma unroll
            for (int g = 0; g < 7; g++) {
                const float v0 = ac[28 + 4 * g + 0], v1 = ac[28 + 4 * g + 1];
                const float v2 = ac[28 + 4 * g + 2], v3 = ac[28 + 4 * g + 3];
                if (!sc) asm volatile("st.async.shared::cluster.mbarrier::complete_tx::bytes.v4.f32 [%0], {%1,%2,%3,%4}, [%5];"
                             ::"r"(rdst + g * 2048), "f"(v0), "f"(v1), "f"(v2), "f"(v3), "r"(rbar) : "memory");
            }
            mbar_wait_cluster(BAR(B_XCH + w), sc);
            PROFC(25);
            uint32_t op[16];
#pragma unroll
            for (int g = 0; g < 7; g++) {
                const uint4 rv = *(const uint4*)(smem + OFF_Y + (5 + w) * 16384 + t * 16 + g * 2048);
                const float2 gb = *(const float2*)(smem + M_G + 224 + (8 * g + 2 * q) * 4);
                const float v0 = ac[4 * g + 0] + __uint_as_float(rv.x), v1 = ac[4 * g + 1] + __uint_as_float(rv.y);
                const float v2 = ac[4 * g + 2] + __uint_as_float(rv.z), v3 = ac[4 * g + 3] + __uint_as_float(rv.w);
                op[2 * g] = pack2(fmaf(gb.x, v0, bf_lo(x1p[2 * g])), fmaf(gb.y, v1, bf_hi(x1p[2 * g])));
                op[2 * g + 1] = pack2(fmaf(gb.x, v2, bf_lo(x1p[2 * g + 1])), fmaf(gb.y, v3, bf_hi(x1p[2 * g + 1])));
            }
            WAIT(B_EMPTY + 1, 0);
            const uint32_t oc = sb + OUT_STAGE + warp * 1792;
            const uint32_t oa = oc + (((lane >> 3) & 1) * 8 + (lane & 7)) * 112 + (lane >> 4) * 16;
            stsm4(oa, op[0], op[1], op[2], op[3]); stsm4(oa + 32, op[4], op[5], op[6], op[7]); stsm4(oa + 64, op[8], op[9], op[10], op[11]);
            asm volatile("stmatrix.sync.aligned.m8n8.x2.shared.b16 [%0], {%1,%2};" ::"r"(oa + 96), "r"(op[12]), "r"(op[13]));
            fence_async_smem();
            __syncwarp();
            asm volatile("{\n.reg .pred p;\nelect.sync _|p, 0xffffffff;\n@p cp.async.bulk.tensor.3d.global.shared::cta.bulk_group [%0, {%2, %3, %4}], [%1];\n"
                         "cp.async.bulk.commit_group;\ncp.async.bulk.wait_group.read 0;\n}" ::"l"(&p.om), "r"(oc), "r"(56 * j), "r"(128 * r + 16 * warp), "r"(0) : "memory");
        }
        PROFC(26);
        bar_sync(1 + w, 128);
        if (wi == 0) warp_arrive(BAR(B_DONE));
        return;
    }
    helper_late(p, r, j, warp PROF_ARGS);
}

#undef act
typedef CUresult (*EncodeFn)(CUtensorMap*, CUtensorMapDataType, cuuint32_t, void*, const cuuint64_t*, const cuuint64_t*, const cuuint32_t*,
                             const cuuint32_t*, CUtensorMapInterleave, CUtensorMapSwizzle, CUtensorMapL2promotion, CUtensorMapFloatOOBfill);

static void make_map(EncodeFn fn, CUtensorMap* m, const void* ptr, uint64_t d0, uint64_t d1, uint64_t d2, uint64_t s1, uint64_t s2,
                     uint32_t b0, uint32_t b1, uint32_t b2, CUtensorMapSwizzle sw) {
    cuuint64_t dims[3] = {d0, d1, d2}, strides[2] = {s1, s2};
    cuuint32_t box[3] = {b0, b1, b2}, es[3] = {1, 1, 1};
    CUresult rc = fn(m, CU_TENSOR_MAP_DATA_TYPE_BFLOAT16, 3, (void*)ptr, dims, strides, box, es, CU_TENSOR_MAP_INTERLEAVE_NONE, sw,
                     CU_TENSOR_MAP_L2_PROMOTION_L2_128B, CU_TENSOR_MAP_FLOAT_OOB_FILL_NONE);
    (void)rc;
}

extern "C" void kernel_launch(void* const* d_in, const int* in_sizes, int n_in, void* d_out, int out_size) {
    (void)in_sizes; (void)n_in; (void)out_size;
    static EncodeFn fn = nullptr;
    static uint32_t* act_base = nullptr;
    if (!fn) {
        cudaDriverEntryPointQueryResult st;
        cudaGetDriverEntryPoint("cuTensorMapEncodeTiled", (void**)&fn, cudaEnableDefault, &st);
        void* a = nullptr;
        cudaGetSymbolAddress(&a, g_act);
        act_base = (uint32_t*)(((uintptr_t)a + 0xFFFFF) & ~(uintptr_t)0xFFFFF);
        cudaFuncSetAttribute(fused_block_kernel, cudaFuncAttributeMaxDynamicSharedMemorySize, SMEM_BYTES);
    }
    Params p;
    p.x = (const bf16*)d_in[0];
    const bf16* wqkv = (const bf16*)d_in[1];
    p.wqkv = wqkv;
    p.wop = (const bf16*)d_in[2];
    p.wg = (const bf16*)d_in[4];
    p.wu = (const bf16*)d_in[5];
    p.wd = (const bf16*)d_in[6];
    p.c = (const bf16*)d_in[7];
    p.wmod = (const bf16*)d_in[8];
    p.out = (bf16*)d_out;
    p.zero = 0;
    p.actb = act_base;
    make_map(fn, &p.wm, p.wmod, 2688, 448, 1, 5376, 5376 * 448, 16, 224, 1, CU_TENSOR_MAP_SWIZZLE_NONE);
    make_map(fn, &p.wm2, p.wmod, 2688, 448, 1, 5376, 5376 * 448, 32, 224, 1, CU_TENSOR_MAP_SWIZZLE_NONE);
    make_map(fn, &p.om, p.out, 448, 2048, 1, 896, 896 * 2048, 56, 16, 1, CU_TENSOR_MAP_SWIZZLE_NONE);
    make_map(fn, &p.xm, p.x, 448, 2048, 1, 896, 896 * 2048, 64, 128, 1, CU_TENSOR_MAP_SWIZZLE_128B);
    make_map(fn, &p.qkv, wqkv, 1344, 448, 1, 2688, 2688 * 448, 64, 224, 1, CU_TENSOR_MAP_SWIZZLE_128B);
    make_map(fn, &p.wo, p.wop, 448, 448, 1, 896, 896 * 448, 64, 224, 1, CU_TENSOR_MAP_SWIZZLE_128B);
    make_map(fn, &p.ga, p.wg, 64, 448, 28, 3584, 128, 64, 32, 2, CU_TENSOR_MAP_SWIZZLE_128B);
    make_map(fn, &p.ua, p.wu, 64, 448, 28, 3584, 128, 64, 32, 2, CU_TENSOR_MAP_SWIZZLE_128B);
    make_map(fn, &p.gb, p.wg, 64, 448, 28, 3584, 128, 64, 64, 1, CU_TENSOR_MAP_SWIZZLE_128B);
    make_map(fn, &p.ub, p.wu, 64, 448, 28, 3584, 128, 64, 64, 1, CU_TENSOR_MAP_SWIZZLE_128B);
    make_map(fn, &p.gc, p.wg, 32, 448, 56, 3584, 64, 32, 64, 1, CU_TENSOR_MAP_SWIZZLE_64B);
    make_map(fn, &p.uc, p.wu, 32, 448, 56, 3584, 64, 32, 64, 1, CU_TENSOR_MAP_SWIZZLE_64B);
    make_map(fn, &p.dn, p.wd, 8, 1792, 56, 896, 16, 8, 32, 7, CU_TENSOR_MAP_SWIZZLE_NONE);
    fused_block_kernel<<<GRID, 384, SMEM_BYTES>>>(p);
}
```

```cpp
#include <cuda_runtime.h>
#include <cuda_bf16.h>
#include <cuda.h>
#include <stdint.h>

typedef __nv_bfloat16 bf16;

template<uint64_t CA, uint64_t CB> __device__ __forceinline__ void wgmma_sk_160(float* d, uint32_t da, uint32_t db, int sd) {
  asm volatile("{\n.reg .pred p;\n.reg .b64 a, b;\nsetp.ne.b32 p, %82, 0;\nmov.b64 a, {%80, %83};\nmov.b64 b, {%81, %84};\n"
    "wgmma.mma_async.sync.aligned.m64n160k16.f32.bf16.bf16 {%0,%1,%2,%3,%4,%5,%6,%7,%8,%9,%10,%11,%12,%13,%14,%15,%16,%17,%18,%19,%20,%21,%22,%23,%24,%25,%26,%27,%28,%29,%30,%31,%32,%33,%34,%35,%36,%37,%38,%39,%40,%41,%42,%43,%44,%45,%46,%47,%48,%49,%50,%51,%52,%53,%54,%55,%56,%57,%58,%59,%60,%61,%62,%63,%64,%65,%66,%67,%68,%69,%70,%71,%72,%73,%74,%75,%76,%77,%78,%79}, a, b, p, 1, 1, 0, 0;\n}\n"
    : "+f"(d[0]),"+f"(d[1]),"+f"(d[2]),"+f"(d[3]),"+f"(d[4]),"+f"(d[5]),"+f"(d[6]),"+f"(d[7]),"+f"(d[8]),"+f"(d[9]),"+f"(d[10]),"+f"(d[11]),"+f"(d[12]),"+f"(d[13]),"+f"(d[14]),"+f"(d[15]),"+f"(d[16]),"+f"(d[17]),"+f"(d[18]),"+f"(d[19]),"+f"(d[20]),"+f"(d[21]),"+f"(d[22]),"+f"(d[23]),"+f"(d[24]),"+f"(d[25]),"+f"(d[26]),"+f"(d[27]),"+f"(d[28]),"+f"(d[29]),"+f"(d[30]),"+f"(d[31]),"+f"(d[32]),"+f"(d[33]),"+f"(d[34]),"+f"(d[35]),"+f"(d[36]),"+f"(d[37]),"+f"(d[38]),"+f"(d[39]),"+f"(d[40]),"+f"(d[41]),"+f"(d[42]),"+f"(d[43]),"+f"(d[44]),"+f"(d[45]),"+f"(d[46]),"+f"(d[47]),"+f"(d[48]),"+f"(d[49]),"+f"(d[50]),"+f"(d[51]),"+f"(d[52]),"+f"(d[53]),"+f"(d[54]),"+f"(d[55]),"+f"(d[56]),"+f"(d[57]),"+f"(d[58]),"+f"(d[59]),"+f"(d[60]),"+f"(d[61]),"+f"(d[62]),"+f"(d[63]),"+f"(d[64]),"+f"(d[65]),"+f"(d[66]),"+f"(d[67]),"+f"(d[68]),"+f"(d[69]),"+f"(d[70]),"+f"(d[71]),"+f"(d[72]),"+f"(d[73]),"+f"(d[74]),"+f"(d[75]),"+f"(d[76]),"+f"(d[77]),"+f"(d[78]),"+f"(d[79])
    : "r"(da), "r"(db), "r"(sd), "n"((uint32_t)(CA >> 32)), "n"((uint32_t)(CB >> 32)));
}
__device__ __forceinline__ void wgmma_rl_56(float* d, uint32_t a0, uint32_t a1, uint32_t a2, uint32_t a3, uint64_t db, int sd) {
  asm volatile("{\n.reg .pred p;\nsetp.ne.b32 p, %33, 0;\n"
    "wgmma.mma_async.sync.aligned.m64n56k16.f32.bf16.bf16 {%0,%1,%2,%3,%4,%5,%6,%7,%8,%9,%10,%11,%12,%13,%14,%15,%16,%17,%18,%19,%20,%21,%22,%23,%24,%25,%26,%27}, {%28,%29,%30,%31}, %32, p, 1, 1, 1;\n}\n"
    : "+f"(d[0]),"+f"(d[1]),"+f"(d[2]),"+f"(d[3]),"+f"(d[4]),"+f"(d[5]),"+f"(d[6]),"+f"(d[7]),"+f"(d[8]),"+f"(d[9]),"+f"(d[10]),"+f"(d[11]),"+f"(d[12]),"+f"(d[13]),"+f"(d[14]),"+f"(d[15]),"+f"(d[16]),"+f"(d[17]),"+f"(d[18]),"+f"(d[19]),"+f"(d[20]),"+f"(d[21]),"+f"(d[22]),"+f"(d[23]),"+f"(d[24]),"+f"(d[25]),"+f"(d[26]),"+f"(d[27])
    : "r"(a0), "r"(a1), "r"(a2), "r"(a3), "l"(db), "r"(sd));
}
template<uint64_t CA, uint64_t CB> __device__ __forceinline__ void wgmma_ss_56(float* d, uint32_t da, uint32_t db, int sd) {
  asm volatile("{\n.reg .pred p;\n.reg .b64 a, b;\nsetp.ne.b32 p, %30, 0;\nmov.b64 a, {%28, %31};\nmov.b64 b, {%29, %32};\n"
    "wgmma.mma_async.sync.aligned.m64n56k16.f32.bf16.bf16 {%0,%1,%2,%3,%4,%5,%6,%7,%8,%9,%10,%11,%12,%13,%14,%15,%16,%17,%18,%19,%20,%21,%22,%23,%24,%25,%26,%27}, a, b, p, 1, 1, 0, 1;\n}\n"
    : "+f"(d[0]),"+f"(d[1]),"+f"(d[2]),"+f"(d[3]),"+f"(d[4]),"+f"(d[5]),"+f"(d[6]),"+f"(d[7]),"+f"(d[8]),"+f"(d[9]),"+f"(d[10]),"+f"(d[11]),"+f"(d[12]),"+f"(d[13]),"+f"(d[14]),"+f"(d[15]),"+f"(d[16]),"+f"(d[17]),"+f"(d[18]),"+f"(d[19]),"+f"(d[20]),"+f"(d[21]),"+f"(d[22]),"+f"(d[23]),"+f"(d[24]),"+f"(d[25]),"+f"(d[26]),"+f"(d[27])
    : "r"(da), "r"(db), "r"(sd), "n"((uint32_t)(CA >> 32)), "n"((uint32_t)(CB >> 32)));
}
__device__ __forceinline__ void wgmma_rl_256(float* d, uint32_t a0, uint32_t a1, uint32_t a2, uint32_t a3, uint64_t db, int sd) {
  asm volatile("{\n.reg .pred p;\nsetp.ne.b32 p, %133, 0;\n"
    "wgmma.mma_async.sync.aligned.m64n256k16.f32.bf16.bf16 {%0,%1,%2,%3,%4,%5,%6,%7,%8,%9,%10,%11,%12,%13,%14,%15,%16,%17,%18,%19,%20,%21,%22,%23,%24,%25,%26,%27,%28,%29,%30,%31,%32,%33,%34,%35,%36,%37,%38,%39,%40,%41,%42,%43,%44,%45,%46,%47,%48,%49,%50,%51,%52,%53,%54,%55,%56,%57,%58,%59,%60,%61,%62,%63,%64,%65,%66,%67,%68,%69,%70,%71,%72,%73,%74,%75,%76,%77,%78,%79,%80,%81,%82,%83,%84,%85,%86,%87,%88,%89,%90,%91,%92,%93,%94,%95,%96,%97,%98,%99,%100,%101,%102,%103,%104,%105,%106,%107,%108,%109,%110,%111,%112,%113,%114,%115,%116,%117,%118,%119,%120,%121,%122,%123,%124,%125,%126,%127}, {%128,%129,%130,%131}, %132, p, 1, 1, 1;\n}\n"
    : "+f"(d[0]),"+f"(d[1]),"+f"(d[2]),"+f"(d[3]),"+f"(d[4]),"+f"(d[5]),"+f"(d[6]),"+f"(d[7]),"+f"(d[8]),"+f"(d[9]),"+f"(d[10]),"+f"(d[11]),"+f"(d[12]),"+f"(d[13]),"+f"(d[14]),"+f"(d[15]),"+f"(d[16]),"+f"(d[17]),"+f"(d[18]),"+f"(d[19]),"+f"(d[20]),"+f"(d[21]),"+f"(d[22]),"+f"(d[23]),"+f"(d[24]),"+f"(d[25]),"+f"(d[26]),"+f"(d[27]),"+f"(d[28]),"+f"(d[29]),"+f"(d[30]),"+f"(d[31]),"+f"(d[32]),"+f"(d[33]),"+f"(d[34]),"+f"(d[35]),"+f"(d[36]),"+f"(d[37]),"+f"(d[38]),"+f"(d[39]),"+f"(d[40]),"+f"(d[41]),"+f"(d[42]),"+f"(d[43]),"+f"(d[44]),"+f"(d[45]),"+f"(d[46]),"+f"(d[47]),"+f"(d[48]),"+f"(d[49]),"+f"(d[50]),"+f"(d[51]),"+f"(d[52]),"+f"(d[53]),"+f"(d[54]),"+f"(d[55]),"+f"(d[56]),"+f"(d[57]),"+f"(d[58]),"+f"(d[59]),"+f"(d[60]),"+f"(d[61]),"+f"(d[62]),"+f"(d[63]),"+f"(d[64]),"+f"(d[65]),"+f"(d[66]),"+f"(d[67]),"+f"(d[68]),"+f"(d[69]),"+f"(d[70]),"+f"(d[71]),"+f"(d[72]),"+f"(d[73]),"+f"(d[74]),"+f"(d[75]),"+f"(d[76]),"+f"(d[77]),"+f"(d[78]),"+f"(d[79]),"+f"(d[80]),"+f"(d[81]),"+f"(d[82]),"+f"(d[83]),"+f"(d[84]),"+f"(d[85]),"+f"(d[86]),"+f"(d[87]),"+f"(d[88]),"+f"(d[89]),"+f"(d[90]),"+f"(d[91]),"+f"(d[92]),"+f"(d[93]),"+f"(d[94]),"+f"(d[95]),"+f"(d[96]),"+f"(d[97]),"+f"(d[98]),"+f"(d[99]),"+f"(d[100]),"+f"(d[101]),"+f"(d[102]),"+f"(d[103]),"+f"(d[104]),"+f"(d[105]),"+f"(d[106]),"+f"(d[107]),"+f"(d[108]),"+f"(d[109]),"+f"(d[110]),"+f"(d[111]),"+f"(d[112]),"+f"(d[113]),"+f"(d[114]),"+f"(d[115]),"+f"(d[116]),"+f"(d[117]),"+f"(d[118]),"+f"(d[119]),"+f"(d[120]),"+f"(d[121]),"+f"(d[122]),"+f"(d[123]),"+f"(d[124]),"+f"(d[125]),"+f"(d[126]),"+f"(d[127])
    : "r"(a0), "r"(a1), "r"(a2), "r"(a3), "l"(db), "r"(sd));
}
template<uint64_t CA, uint64_t CB> __device__ __forceinline__ void wgmma_ss_128(float* d, uint32_t da, uint32_t db, int sd) {
  asm volatile("{\n.reg .pred p;\n.reg .b64 a, b;\nsetp.ne.b32 p, %66, 0;\nmov.b64 a, {%64, %67};\nmov.b64 b, {%65, %68};\n"
    "wgmma.mma_async.sync.aligned.m64n128k16.f32.bf16.bf16 {%0,%1,%2,%3,%4,%5,%6,%7,%8,%9,%10,%11,%12,%13,%14,%15,%16,%17,%18,%19,%20,%21,%22,%23,%24,%25,%26,%27,%28,%29,%30,%31,%32,%33,%34,%35,%36,%37,%38,%39,%40,%41,%42,%43,%44,%45,%46,%47,%48,%49,%50,%51,%52,%53,%54,%55,%56,%57,%58,%59,%60,%61,%62,%63}, a, b, p, 1, 1, 0, 1;\n}\n"
    : "+f"(d[0]),"+f"(d[1]),"+f"(d[2]),"+f"(d[3]),"+f"(d[4]),"+f"(d[5]),"+f"(d[6]),"+f"(d[7]),"+f"(d[8]),"+f"(d[9]),"+f"(d[10]),"+f"(d[11]),"+f"(d[12]),"+f"(d[13]),"+f"(d[14]),"+f"(d[15]),"+f"(d[16]),"+f"(d[17]),"+f"(d[18]),"+f"(d[19]),"+f"(d[20]),"+f"(d[21]),"+f"(d[22]),"+f"(d[23]),"+f"(d[24]),"+f"(d[25]),"+f"(d[26]),"+f"(d[27]),"+f"(d[28]),"+f"(d[29]),"+f"(d[30]),"+f"(d[31]),"+f"(d[32]),"+f"(d[33]),"+f"(d[34]),"+f"(d[35]),"+f"(d[36]),"+f"(d[37]),"+f"(d[38]),"+f"(d[39]),"+f"(d[40]),"+f"(d[41]),"+f"(d[42]),"+f"(d[43]),"+f"(d[44]),"+f"(d[45]),"+f"(d[46]),"+f"(d[47]),"+f"(d[48]),"+f"(d[49]),"+f"(d[50]),"+f"(d[51]),"+f"(d[52]),"+f"(d[53]),"+f"(d[54]),"+f"(d[55]),"+f"(d[56]),"+f"(d[57]),"+f"(d[58]),"+f"(d[59]),"+f"(d[60]),"+f"(d[61]),"+f"(d[62]),"+f"(d[63])
    : "r"(da), "r"(db), "r"(sd), "n"((uint32_t)(CA >> 32)), "n"((uint32_t)(CB >> 32)));
}
template<uint64_t CA, uint64_t CB> __device__ __forceinline__ void wgmma_ss_64(float* d, uint32_t da, uint32_t db, int sd) {
  asm volatile("{\n.reg .pred p;\n.reg .b64 a, b;\nsetp.ne.b32 p, %34, 0;\nmov.b64 a, {%32, %35};\nmov.b64 b, {%33, %36};\n"
    "wgmma.mma_async.sync.aligned.m64n64k16.f32.bf16.bf16 {%0,%1,%2,%3,%4,%5,%6,%7,%8,%9,%10,%11,%12,%13,%14,%15,%16,%17,%18,%19,%20,%21,%22,%23,%24,%25,%26,%27,%28,%29,%30,%31}, a, b, p, 1, 1, 0, 1;\n}\n"
    : "+f"(d[0]),"+f"(d[1]),"+f"(d[2]),"+f"(d[3]),"+f"(d[4]),"+f"(d[5]),"+f"(d[6]),"+f"(d[7]),"+f"(d[8]),"+f"(d[9]),"+f"(d[10]),"+f"(d[11]),"+f"(d[12]),"+f"(d[13]),"+f"(d[14]),"+f"(d[15]),"+f"(d[16]),"+f"(d[17]),"+f"(d[18]),"+f"(d[19]),"+f"(d[20]),"+f"(d[21]),"+f"(d[22]),"+f"(d[23]),"+f"(d[24]),"+f"(d[25]),"+f"(d[26]),"+f"(d[27]),"+f"(d[28]),"+f"(d[29]),"+f"(d[30]),"+f"(d[31])
    : "r"(da), "r"(db), "r"(sd), "n"((uint32_t)(CA >> 32)), "n"((uint32_t)(CB >> 32)));
}
template<uint64_t CA, uint64_t CB> __device__ __forceinline__ void wgmma_ss_112(float* d, uint32_t da, uint32_t db, int sd) {
  asm volatile("{\n.reg .pred p;\n.reg .b64 a, b;\nsetp.ne.b32 p, %58, 0;\nmov.b64 a, {%56, %59};\nmov.b64 b, {%57, %60};\n"
    "wgmma.mma_async.sync.aligned.m64n112k16.f32.bf16.bf16 {%0,%1,%2,%3,%4,%5,%6,%7,%8,%9,%10,%11,%12,%13,%14,%15,%16,%17,%18,%19,%20,%21,%22,%23,%24,%25,%26,%27,%28,%29,%30,%31,%32,%33,%34,%35,%36,%37,%38,%39,%40,%41,%42,%43,%44,%45,%46,%47,%48,%49,%50,%51,%52,%53,%54,%55}, a, b, p, 1, 1, 0, 1;\n}\n"
    : "+f"(d[0]),"+f"(d[1]),"+f"(d[2]),"+f"(d[3]),"+f"(d[4]),"+f"(d[5]),"+f"(d[6]),"+f"(d[7]),"+f"(d[8]),"+f"(d[9]),"+f"(d[10]),"+f"(d[11]),"+f"(d[12]),"+f"(d[13]),"+f"(d[14]),"+f"(d[15]),"+f"(d[16]),"+f"(d[17]),"+f"(d[18]),"+f"(d[19]),"+f"(d[20]),"+f"(d[21]),"+f"(d[22]),"+f"(d[23]),"+f"(d[24]),"+f"(d[25]),"+f"(d[26]),"+f"(d[27]),"+f"(d[28]),"+f"(d[29]),"+f"(d[30]),"+f"(d[31]),"+f"(d[32]),"+f"(d[33]),"+f"(d[34]),"+f"(d[35]),"+f"(d[36]),"+f"(d[37]),"+f"(d[38]),"+f"(d[39]),"+f"(d[40]),"+f"(d[41]),"+f"(d[42]),"+f"(d[43]),"+f"(d[44]),"+f"(d[45]),"+f"(d[46]),"+f"(d[47]),"+f"(d[48]),"+f"(d[49]),"+f"(d[50]),"+f"(d[51]),"+f"(d[52]),"+f"(d[53]),"+f"(d[54]),"+f"(d[55])
    : "r"(da), "r"(db), "r"(sd), "n"((uint32_t)(CA >> 32)), "n"((uint32_t)(CB >> 32)));
}
__device__ __forceinline__ void wgmma_rl_112(float* d, uint32_t a0, uint32_t a1, uint32_t a2, uint32_t a3, uint64_t db, int sd) {
  asm volatile("{\n.reg .pred p;\nsetp.ne.b32 p, %61, 0;\n"
    "wgmma.mma_async.sync.aligned.m64n112k16.f32.bf16.bf16 {%0,%1,%2,%3,%4,%5,%6,%7,%8,%9,%10,%11,%12,%13,%14,%15,%16,%17,%18,%19,%20,%21,%22,%23,%24,%25,%26,%27,%28,%29,%30,%31,%32,%33,%34,%35,%36,%37,%38,%39,%40,%41,%42,%43,%44,%45,%46,%47,%48,%49,%50,%51,%52,%53,%54,%55}, {%56,%57,%58,%59}, %60, p, 1, 1, 1;\n}\n"
    : "+f"(d[0]),"+f"(d[1]),"+f"(d[2]),"+f"(d[3]),"+f"(d[4]),"+f"(d[5]),"+f"(d[6]),"+f"(d[7]),"+f"(d[8]),"+f"(d[9]),"+f"(d[10]),"+f"(d[11]),"+f"(d[12]),"+f"(d[13]),"+f"(d[14]),"+f"(d[15]),"+f"(d[16]),"+f"(d[17]),"+f"(d[18]),"+f"(d[19]),"+f"(d[20]),"+f"(d[21]),"+f"(d[22]),"+f"(d[23]),"+f"(d[24]),"+f"(d[25]),"+f"(d[26]),"+f"(d[27]),"+f"(d[28]),"+f"(d[29]),"+f"(d[30]),"+f"(d[31]),"+f"(d[32]),"+f"(d[33]),"+f"(d[34]),"+f"(d[35]),"+f"(d[36]),"+f"(d[37]),"+f"(d[38]),"+f"(d[39]),"+f"(d[40]),"+f"(d[41]),"+f"(d[42]),"+f"(d[43]),"+f"(d[44]),"+f"(d[45]),"+f"(d[46]),"+f"(d[47]),"+f"(d[48]),"+f"(d[49]),"+f"(d[50]),"+f"(d[51]),"+f"(d[52]),"+f"(d[53]),"+f"(d[54]),"+f"(d[55])
    : "r"(a0), "r"(a1), "r"(a2), "r"(a3), "l"(db), "r"(sd));
}

constexpr int DM = 448;
constexpr int NCTA = 128;
#define MAPPING 1
#define GRID 128
#define PINGPONG 0
#define WIN 6
#define WIN_END 25
#define UNR_B 1
#define UNR_C 1
constexpr int kB = UNR_B, kC = UNR_C;
#define LIKELY(x) __builtin_expect(!!(x), 1)
#define PACE 1
#define PACE_END 6
#define GEMV_AT 1
#define NPRE 14
#define ATT_OFF 0
#define ATT_WG 1
#define XFIRST 7
#define KDELAY 0
#define KEARLY 1
#define MAP_S 4
constexpr int SPIN_LIMIT = 1 << 22;

constexpr uint32_t OFF_X = 0, OFF_Y = 114688, OFF_MISC = 229376, SMEM_BYTES = 232448;
constexpr uint32_t Y_VR = 0, Y_K = 28672, Y_KOWN = 57344, Y_VOWN = 71680, Y_Q = 86016;
constexpr uint32_t HALF = 57344;
constexpr uint32_t X_STAT = 49152;
constexpr uint32_t OUT_STAGE = 16384;
constexpr uint32_t M_BAR = OFF_MISC;
constexpr uint32_t M_ST = OFF_MISC + 512;
constexpr uint32_t M_G = OFF_MISC + 2304;
constexpr uint32_t M_EPOCH = OFF_MISC + 3040;
enum { B_XFULL = 0, B_FULLK = 7, B_FULLV = 8, B_FULLQ, B_KRFULL, B_VRFULL, B_WOFULL, B_XCH, B_MOD1 = 15, B_FULL = 16, B_WMFULL = 30,
       B_EMPTY = 32, B_XFREE = B_EMPTY + 12, B_GEMV, B_PEER,
       B_PUB = 47,
       B_WMFREE = 56, B_HRDY, B_GFULL = B_HRDY + 3, B_DONE = 31, B_DUMMY = B_GEMV };

__device__ uint32_t g_ticket;
__device__ __align__(128) uint32_t g_mod[8 * 6 * DM];
__device__ __align__(128) uint32_t g_flag[144 * 128];
constexpr int RB_WORDS = 262144, RB_KV = 0, RB_O = 57344, RB_X1 = 86016, RB_H2 = 143360, RB_ST = 258048;
__device__ __align__(128) uint32_t g_act[18 * RB_WORDS];
__device__ __align__(128) uint32_t g_wd[56 * 4 * 1792];
#define PROFH(id)
#define PROFH1(id)
#define PROFC(id)

struct alignas(64) Params {
    CUtensorMap wm, wm2, om, xm, qkv, wo, ga, ua, gb, ub, gc, uc, dn;
    const bf16 *x, *c, *wqkv, *wmod, *wg, *wu, *wd, *wop;
    bf16* out;
    uint32_t* actb;
    uint32_t zero;
};

__device__ __forceinline__ void mbar_init(uint32_t bar, int cnt) { asm volatile("mbarrier.init.shared::cta.b64 [%0], %1;" ::"r"(bar), "r"(cnt) : "memory"); }
__device__ __forceinline__ void mbar_expect_tx(uint32_t bar, uint32_t bytes) { asm volatile("mbarrier.arrive.expect_tx.shared::cta.b64 _, [%0], %1;" ::"r"(bar), "r"(bytes) : "memory"); }
__device__ __forceinline__ void mbar_arrive(uint32_t bar) { asm volatile("mbarrier.arrive.shared::cta.b64 _, [%0];" ::"r"(bar) : "memory"); }
__device__ __forceinline__ void mbar_wait(uint32_t bar, uint32_t parity) {
    uint32_t ok; int n = 0;
    do {
        asm volatile("{\n.reg .pred p;\nmbarrier.try_wait.parity.shared::cta.b64 p, [%1], %2;\nselp.u32 %0, 1, 0, p;\n}" : "=r"(ok) : "r"(bar), "r"(parity) : "memory");
        if (++n > SPIN_LIMIT) __trap();
    } while (!ok);
}
__device__ __forceinline__ void mbar_wait_c(uint32_t bar, uint32_t parity) {
    asm volatile("{\n.reg .pred p;\nWL:\nmbarrier.try_wait.parity.shared::cta.b64 p, [%0], %1, 0x989680;\n@!p bra WL;\n}" ::"r"(bar), "r"(parity) : "memory");
}
__device__ __forceinline__ void mbar_wait_cluster(uint32_t bar, uint32_t parity) {
    asm volatile("{\n.reg .pred p;\nWL:\nmbarrier.try_wait.parity.acquire.cluster.shared::cta.b64 p, [%0], %1, 0x989680;\n@!p bra WL;\n}" ::"r"(bar), "r"(parity) : "memory");
}
__device__ __forceinline__ void warp_arrive(uint32_t bar) {
    __syncwarp();
    asm volatile("{\n.reg .pred p;\nelect.sync _|p, 0xffffffff;\n@p mbarrier.arrive.shared::cta.b64 _, [%0];\n}" ::"r"(bar) : "memory");
}
__device__ __forceinline__ int opaque(int v) { return __shfl_sync(~0u, v, 0); }
__device__ __forceinline__ int fresh_tid() { int v; asm volatile("mov.u32 %0, %%tid.x;" : "=r"(v)); return v; }
__device__ __forceinline__ void bar_sync(int id, int n) { asm volatile("bar.sync %0, %1;" ::"r"(id), "r"(n) : "memory"); }
__device__ __forceinline__ void bar_arrive(int id, int n) { asm volatile("bar.arrive %0, %1;" ::"r"(id), "r"(n) : "memory"); }
__device__ __forceinline__ void fence_async_smem() { asm volatile("fence.proxy.async.shared::cta;" ::: "memory"); }
__device__ __forceinline__ void fence_async_global() { asm volatile("fence.proxy.async.global;" ::: "memory"); }
__device__ __forceinline__ void fence_gpu() { asm volatile("fence.release.gpu;" ::: "memory"); }
__device__ __forceinline__ void tma3(uint32_t dst, const CUtensorMap* m, int c0, int c1, int c2, uint32_t bar) {
    asm volatile("cp.async.bulk.tensor.3d.shared::cluster.global.mbarrier::complete_tx::bytes [%0], [%1, {%3, %4, %5}], [%2];"
                 ::"r"(dst), "l"(m), "r"(bar), "r"(c0), "r"(c1), "r"(c2) : "memory");
}
__device__ __forceinline__ void bulk_load(uint32_t dst, const void* src, uint32_t bytes, uint32_t bar) {
    asm volatile("cp.async.bulk.shared::cluster.global.mbarrier::complete_tx::bytes [%0], [%1], %2, [%3];" ::"r"(dst), "l"(src), "r"(bytes), "r"(bar) : "memory");
}
__device__ __forceinline__ void expect_e(uint32_t bar, uint32_t bytes) {
    asm volatile("{\n.reg .pred p;\nelect.sync _|p, 0xffffffff;\n@p mbarrier.arrive.expect_tx.shared::cta.b64 _, [%0], %1;\n}" ::"r"(bar), "r"(bytes) : "memory");
}
__device__ __forceinline__ void tma3_e(uint32_t dst, const CUtensorMap* m, int c0, int c1, int c2, uint32_t bar) {
    asm volatile("{\n.reg .pred p;\nelect.sync _|p, 0xffffffff;\n@p cp.async.bulk.tensor.3d.shared::cluster.global.mbarrier::complete_tx::bytes [%0], [%1, {%3, %4, %5}], [%2];\n}"
                 ::"r"(dst), "l"(m), "r"(bar), "r"(c0), "r"(c1), "r"(c2) : "memory");
}
__device__ __forceinline__ void bulk_e(uint32_t dst, const void* src, uint32_t bytes, uint32_t bar) {
    asm volatile("{\n.reg .pred p;\nelect.sync _|p, 0xffffffff;\n@p cp.async.bulk.shared::cluster.global.mbarrier::complete_tx::bytes [%0], [%1], %2, [%3];\n}"
                 ::"r"(dst), "l"(src), "r"(bytes), "r"(bar) : "memory");
}
__device__ __forceinline__ void init_e(uint32_t bar, int cnt) {
    asm volatile("{\n.reg .pred p;\nelect.sync _|p, 0xffffffff;\n@p mbarrier.init.shared::cta.b64 [%0], %1;\n}" ::"r"(bar), "r"(cnt) : "memory");
}
__device__ __forceinline__ void l2_prefetch_e(const void* src, uint32_t bytes) {
    asm volatile("{\n.reg .pred p;\nelect.sync _|p, 0xffffffff;\n@p cp.async.bulk.prefetch.L2.global [%0], %1;\n}" ::"l"(src), "r"(bytes) : "memory");
}
__device__ __forceinline__ uint32_t ld_relaxed(const uint32_t* p) { uint32_t v; asm volatile("ld.relaxed.gpu.global.u32 %0, [%1];" : "=r"(v) : "l"(p) : "memory"); return v; }
__device__ __forceinline__ void st_relaxed(uint32_t* p, uint32_t v) { asm volatile("st.relaxed.gpu.global.u32 [%0], %1;" ::"l"(p), "r"(v) : "memory"); }
__device__ __forceinline__ uint4 ld_relaxed4(const uint4* p) { uint4 v; asm volatile("ld.relaxed.gpu.global.v4.u32 {%0,%1,%2,%3}, [%4];" : "=r"(v.x), "=r"(v.y), "=r"(v.z), "=r"(v.w) : "l"(p) : "memory"); return v; }
__device__ __forceinline__ void st_relaxed4(uint4* p, uint4 v) { asm volatile("st.relaxed.gpu.global.v4.u32 [%0], {%1,%2,%3,%4};" ::"l"(p), "r"(v.x), "r"(v.y), "r"(v.z), "r"(v.w) : "memory"); }
__device__ __forceinline__ uint4 ldg_nc4(const void* p) { uint4 v; asm volatile("ld.global.nc.L1::no_allocate.v4.u32 {%0,%1,%2,%3}, [%4];" : "=r"(v.x), "=r"(v.y), "=r"(v.z), "=r"(v.w) : "l"(p)); return v; }
__device__ __forceinline__ uint32_t ldg_nc(const void* p) { uint32_t v; asm volatile("ld.global.nc.u32 %0, [%1];" : "=r"(v) : "l"(p)); return v; }
__device__ __forceinline__ uint32_t ld_acquire(const uint32_t* p) { uint32_t v; asm volatile("ld.acquire.gpu.global.u32 %0, [%1];" : "=r"(v) : "l"(p) : "memory"); return v; }
__device__ __forceinline__ uint4 lds4(uint32_t a) { uint4 v; asm volatile("ld.shared.v4.u32 {%0,%1,%2,%3}, [%4];" : "=r"(v.x), "=r"(v.y), "=r"(v.z), "=r"(v.w) : "r"(a) : "memory"); return v; }
__device__ __forceinline__ float2 lds2f(uint32_t a) { float2 v; asm volatile("ld.shared.v2.f32 {%0,%1}, [%2];" : "=f"(v.x), "=f"(v.y) : "r"(a) : "memory"); return v; }
__device__ __forceinline__ uint32_t lds1(uint32_t a) { uint32_t v; asm volatile("ld.shared.u32 %0, [%1];" : "=r"(v) : "r"(a) : "memory"); return v; }
__device__ __forceinline__ void sts4(uint32_t a, uint4 v) { asm volatile("st.shared.v4.u32 [%0], {%1,%2,%3,%4};" ::"r"(a), "r"(v.x), "r"(v.y), "r"(v.z), "r"(v.w) : "memory"); }
__device__ __forceinline__ void sts2(uint32_t a, uint32_t x, uint32_t y) { asm volatile("st.shared.v2.u32 [%0], {%1,%2};" ::"r"(a), "r"(x), "r"(y) : "memory"); }
__device__ __forceinline__ void sts1(uint32_t a, uint32_t v) { asm volatile("st.shared.u32 [%0], %1;" ::"r"(a), "r"(v) : "memory"); }
__device__ __forceinline__ void stsm4(uint32_t a, uint32_t r0, uint32_t r1, uint32_t r2, uint32_t r3) {
    asm volatile("stmatrix.sync.aligned.m8n8.x4.shared.b16 [%0], {%1,%2,%3,%4};" ::"r"(a), "r"(r0), "r"(r1), "r"(r2), "r"(r3));
}
__device__ __forceinline__ uint32_t pack2(float lo, float hi) { uint32_t r; asm("cvt.rn.bf16x2.f32 %0, %1, %2;" : "=r"(r) : "f"(hi), "f"(lo)); return r; }
__device__ __forceinline__ uint32_t pack2_relu(float lo, float hi) { uint32_t r; asm("cvt.rn.relu.bf16x2.f32 %0, %1, %2;" : "=r"(r) : "f"(hi), "f"(lo)); return r; }
__device__ __forceinline__ uint32_t hfma2(uint32_t a, uint32_t b, uint32_t c) { uint32_t r; asm("fma.rn.bf16x2 %0, %1, %2, %3;" : "=r"(r) : "r"(a), "r"(b), "r"(c)); return r; }
__device__ __forceinline__ uint32_t hmul2(uint32_t a, uint32_t b) { uint32_t r; asm("mul.rn.bf16x2 %0, %1, %2;" : "=r"(r) : "r"(a), "r"(b)); return r; }
__device__ __forceinline__ float bf_lo(uint32_t v) { return __uint_as_float(v << 16); }
__device__ __forceinline__ float bf_hi(uint32_t v) { return __uint_as_float(v & 0xFFFF0000u); }
__device__ __forceinline__ float bf_round(float v) { return bf_lo(pack2(v, 0.f)); }
__device__ __forceinline__ float ex2(float x) { float r; asm("ex2.approx.ftz.f32 %0, %1;" : "=f"(r) : "f"(x)); return r; }
__device__ __forceinline__ void mma16816(float* d, uint32_t a0, uint32_t a1, uint32_t a2, uint32_t a3, uint32_t b0, uint32_t b1) {
    asm("mma.sync.aligned.m16n8k16.row.col.f32.bf16.bf16.f32 {%0,%1,%2,%3}, {%4,%5,%6,%7}, {%8,%9}, {%0,%1,%2,%3};"
        : "+f"(d[0]), "+f"(d[1]), "+f"(d[2]), "+f"(d[3]) : "r"(a0), "r"(a1), "r"(a2), "r"(a3), "r"(b0), "r"(b1));
}
__device__ __forceinline__ void mma16816_first(float* d, uint32_t a0, uint32_t a1, uint32_t a2, uint32_t a3, uint32_t b0, uint32_t b1) {
    asm volatile("mma.sync.aligned.m16n8k16.row.col.f32.bf16.bf16.f32 {%0,%1,%2,%3}, {%4,%5,%6,%7}, {%8,%9}, {%10,%10,%10,%10};"
        : "=f"(d[0]), "=f"(d[1]), "=f"(d[2]), "=f"(d[3]) : "r"(a0), "r"(a1), "r"(a2), "r"(a3), "r"(b0), "r"(b1), "f"(0.f));
}
__device__ __forceinline__ void mma16816_v(float* d, uint32_t a0, uint32_t a1, uint32_t a2, uint32_t a3, uint32_t b0, uint32_t b1) {
    asm volatile("mma.sync.aligned.m16n8k16.row.col.f32.bf16.bf16.f32 {%0,%1,%2,%3}, {%4,%5,%6,%7}, {%8,%9}, {%0,%1,%2,%3};"
        : "+f"(d[0]), "+f"(d[1]), "+f"(d[2]), "+f"(d[3]) : "r"(a0), "r"(a1), "r"(a2), "r"(a3), "r"(b0), "r"(b1));
}
__device__ __forceinline__ void mma1688(float* d, uint32_t a0, uint32_t a1, uint32_t b0) {
    asm("mma.sync.aligned.m16n8k8.row.col.f32.bf16.bf16.f32 {%0,%1,%2,%3}, {%4,%5}, {%6}, {%0,%1,%2,%3};"
        : "+f"(d[0]), "+f"(d[1]), "+f"(d[2]), "+f"(d[3]) : "r"(a0), "r"(a1), "r"(b0));
}
__device__ __forceinline__ void ldsm4(uint32_t a, uint32_t* r) {
    asm volatile("ldmatrix.sync.aligned.m8n8.x4.shared.b16 {%0,%1,%2,%3}, [%4];" : "=r"(r[0]), "=r"(r[1]), "=r"(r[2]), "=r"(r[3]) : "r"(a));
}
__device__ __forceinline__ void ldsm4t(uint32_t a, uint32_t* r) {
    asm volatile("ldmatrix.sync.aligned.m8n8.x4.trans.shared.b16 {%0,%1,%2,%3}, [%4];" : "=r"(r[0]), "=r"(r[1]), "=r"(r[2]), "=r"(r[3]) : "r"(a));
}
__device__ __forceinline__ uint32_t nz(uint32_t v) { uint32_t r; asm("max.u32 %0, %1, 1;" : "=r"(r) : "r"(v)); return r; }
__device__ __forceinline__ float rcp(float x) { float r; asm("rcp.approx.ftz.f32 %0, %1;" : "=f"(r) : "f"(x)); return r; }
__device__ __forceinline__ uint2 ld_relaxed2(const void* p) { uint2 v; asm volatile("ld.relaxed.gpu.global.v2.u32 {%0,%1}, [%2];" : "=r"(v.x), "=r"(v.y) : "l"(p) : "memory"); return v; }
__device__ __forceinline__ void st_relaxed2(void* p, uint32_t x, uint32_t y) { asm volatile("st.relaxed.gpu.global.v2.u32 [%0], {%1,%2};" ::"l"(p), "r"(max(x, 1u)), "r"(max(y, 1u)) : "memory"); }
__host__ __device__ constexpr uint64_t dconst(uint32_t lbo, uint32_t sbo, uint32_t swz) {
    return ((uint64_t)(lbo >> 4) << 16) | ((uint64_t)(sbo >> 4) << 32) | ((uint64_t)swz << 62);
}
__device__ __forceinline__ uint32_t mkdesc(uint32_t addr, uint64_t c) { return (uint32_t)c | ((addr & 0x3FFFF) >> 4); }
#define WG_FENCE() asm volatile("wgmma.fence.sync.aligned;" ::: "memory")
#define WG_COMMIT() asm volatile("wgmma.commit_group.sync.aligned;" ::: "memory")
#define WG_WAIT(n) asm volatile("wgmma.wait_group.sync.aligned %0;" ::"n"(n) : "memory")
template <int N> __device__ __forceinline__ void reg_fence(float* d) {
#pragma unroll
    for (int i = 0; i < N; i++) asm volatile("" : "+f"(d[i])::"memory");
}
template <int N> __device__ __forceinline__ void reg_def(float* d) {
#pragma unroll
    for (int i = 0; i < N; i++) asm volatile("" : "=f"(d[i]));
}
template <int N> __device__ __forceinline__ void reg_def(uint32_t* d) {
#pragma unroll
    for (int i = 0; i < N; i++) asm volatile("" : "=r"(d[i]));
}
__device__ __forceinline__ bool is_unset(uint4 v) { return min(min(v.x, v.y), min(v.z, v.w)) == 0u; }
__device__ __forceinline__ uint4 nz4(uint32_t a, uint32_t b, uint32_t c, uint32_t d) { return make_uint4(max(a, 1u), max(b, 1u), max(c, 1u), max(d, 1u)); }
__device__ __forceinline__ void wait_flags(const uint32_t* p, uint32_t target, uint32_t mask) {
    int n = 0;
    while (~__ballot_sync(~0u, (int)(ld_relaxed(p) - target) >= 0) & mask) { if (++n > SPIN_LIMIT) __trap(); }
    asm volatile("fence.acquire.gpu;" ::: "memory");
}
__device__ __forceinline__ float silu_bf(uint32_t cbits) {
    const float c = __uint_as_float(cbits << 16);
    return bf_round(__fdividef(c, 1.f + fminf(ex2(-1.4426950408889634f * c), 1e30f)));
}
__device__ __forceinline__ void gemv_part(uint32_t wmbuf, int wp, int lane) {
    const uint32_t wa = wmbuf + wp * 512 + (8 * (lane >> 4) + (lane & 7)) * 32 + ((lane >> 3) & 1) * 16;
    float d[4] = {};
#pragma unroll
    for (int i = 0; i < 4; i++) {
        uint32_t A[4];
        const float2 v = lds2f(wmbuf + 28672 + (wp + 8 * i) * 32 + (lane & 3) * 8);
        ldsm4t(wa + (i < 3 || wp < 4 ? i : 0) * 4096, A);
        mma16816(d, A[0], A[1], A[2], A[3], __float_as_uint(v.x), __float_as_uint(v.y));
    }
    if ((lane & 3) == 0) {
        sts1(wmbuf + 29696 + (wp * 16 + (lane >> 2)) * 4, __float_as_uint(d[0]));
        sts1(wmbuf + 29696 + (wp * 16 + 8 + (lane >> 2)) * 4, __float_as_uint(d[2]));
    }
}
__device__ __forceinline__ uint32_t mod_word(float v, int col, uint32_t target) {
    v = bf_round(v);
    if ((col >= DM && col < 2 * DM) || (col >= 4 * DM && col < 5 * DM)) v += 1.f;
    return (pack2(v, 0.f) << 16) | (target & 0xFFFFu);
}
__device__ __forceinline__ const uint4* mod_src(int i, int r, int j, bool p2) {
    i = min(i, p2 ? 251 : 223);
    return (const uint4*)g_mod + (r & 7) * (6 * DM / 4) + (i < 224 ? (p2 ? 336 : 0) + i : (i < 238 ? 14 * j + i : 14 * j + i + 322));
}
__device__ __forceinline__ void mod_store(uint32_t sb, uint4 v, const uint4* src, int i) {
    const uint32_t tag = lds1(sb + M_EPOCH) + 1;
    while (__any_sync(~0u, (((v.x ^ tag) | (v.y ^ tag) | (v.z ^ tag) | (v.w ^ tag)) & 0xFFFFu) != 0u)) v = ld_relaxed4(src);
    if (i < 224) {
        const int isc = i >= 112, c4 = i - 112 * isc;
        const uint32_t a = sb + M_ST + (c4 >> 2) * 64 + (c4 & 1) * 32 + (c4 & 2) * 4 + (isc ? 0 : 4);
        sts1(a, __byte_perm(v.x, v.y, 0x7632));
        sts1(a + 16, __byte_perm(v.z, v.w, 0x7632));
    } else if (i < 252) {
        sts4(sb + M_G + (i - 224) * 16, make_uint4(v.x & 0xFFFF0000u, v.y & 0xFFFF0000u, v.z & 0xFFFF0000u, v.w & 0xFFFF0000u));
    }
}
__device__ __forceinline__ int pass_f(int fs, int ps) { return 224 * fs + ((fs & 1) ? (ps == 0 ? 96 : ps == 1 ? 32 : 0) : (ps == 0 ? 0 : ps == 1 ? 128 : 192)); }
__device__ __forceinline__ constexpr uint32_t slot_off(int l) { return l * 16384; }
__device__ __forceinline__ constexpr int g1_slot(int s) { return s % 7; }
__device__ __noinline__ void x1_fix(const uint32_t* g, uint32_t sa, int s) {
#pragma unroll 1
    for (int k = 4 * s; k < 4 * s + 4;) {
        const uint4 v = ld_relaxed4((const uint4*)(g + k * 256));
        sts4(sa + k * 1024, v);
        k += 2 * __all_sync(~0u, min(min(v.x, v.y), min(v.z, v.w)) != 0u);
    }
    __syncwarp();
}
__device__ __forceinline__ void ln_coeffs(float mean, float msq, uint32_t& r2, uint32_t& n2) {
    const float rs = bf_round(rsqrtf(fmaxf(msq - mean * mean, 0.f) + 1e-5f));
    r2 = pack2(rs, rs);
    n2 = pack2(-mean * rs, -mean * rs);
}

#define LOADW bulk_e(dst, g_wd + (size_t)((f >> 5) * 4 + nq) * 1792, 7168, bar);
template <int sec> __device__ __forceinline__ void ring_loader(const Params& p, uint32_t sb_, int r_, int j_, int lane) {
    const uint32_t sb = opaque(sb_);
    const int r = opaque(r_), j = opaque(j_), nq = j >> 1, fs = 4 * (j & 1) + nq;
    const int fa = pass_f(fs, 0), fb = pass_f(fs, 1), fc = pass_f(fs, 2);
    const uint32_t* h2src = (const uint32_t*)__shfl_sync(~0u, (unsigned long long)(p.actb + (size_t)r * RB_WORDS + RB_H2), 0);
    const CUtensorMap* gmap = (const CUtensorMap*)__shfl_sync(~0u, (unsigned long long)(&p.ga + sec), 0);
#define BAR(i) (sb + M_BAR + 8 * (i))
#define kh (j & 1)
            int sl = 0;
#pragma unroll 1
            for (int s = 0; s < 28; s++) {
                if (s == 7) { wait_flags(g_flag + (8 * r + j) * 128 + 96 + lane, lds1(sb + M_EPOCH) + 1, 0xFFFFu); fence_async_global(); }
                const int ps = s < 14 ? 0 : s < 21 ? 1 : 2;
                const uint32_t half = ps < 2 ? 8192 : 4096;
                const int sp = sl;
                if (s >= PACE && s < PACE_END) mbar_wait(BAR(B_FULL + s - PACE), 0);
                mbar_wait(BAR(B_EMPTY + sp), (s >= 7 && s < 14) || s >= 21);
                expect_e(BAR(B_FULL + sp), half);
                tma3_e(sb + slot_off(sp) + sec * half, gmap + 2 * ps, 0, ps ? 64 * sl : 32 * s, ps == 0 ? fa >> 6 : ps == 1 ? fb >> 6 : fc >> 5, BAR(B_FULL + sp));
                sl = sl == 6 ? 0 : sl + 1;
            }
            if (!sec) PROFH(3);
#pragma unroll 1
            for (int e = 0; e < 4; e++) {
                const uint32_t dst = sb + slot_off(e) + sec * 8192, bar = BAR(B_FULL + e);
                const int f = (e < 2 ? fa + 64 * e : e == 2 ? fb : fc) + 32 * sec;
                mbar_wait(BAR(B_EMPTY + e), 0);
                expect_e(bar, e == 3 && sec ? 0 : 7168);
                if (!(e == 3 && sec)) { LOADW }
            }
            sl = 4;
            int e = 4;
#pragma unroll 1
            for (int grp = 0; grp < 9; grp++) {
                const int ps = grp >= 6 ? 2 : grp >= 3 ? 1 : 0;
                int sidx = grp - 3 * ps;
                if (sec && sidx == 0) { mbar_wait(BAR(B_HRDY + ps), 0); fence_async_global(); }
                sidx += sidx >= nq;
                int f = pass_f(4 * kh + sidx, ps);
#pragma unroll 1
                for (int k = 4 >> ps; k > 0; k--, e++, f += 32) {
                    const uint32_t dst = sb + slot_off(sl), bar = BAR(B_FULL + sl);
                    mbar_wait(BAR(B_EMPTY + sl), e >= 12 && e < 24);
                    if (e < WIN_END && e >= WIN) mbar_wait(BAR(B_FULL + (sl >= WIN ? sl - WIN : sl + 12 - WIN)), e - WIN >= 12);
                    expect_e(bar, sec ? 8192 : 7168);
                    if (!sec) { LOADW }
                    else bulk_e(dst + 8192, h2src + f * 64, 8192, bar);
                    sl = sl == 11 ? 0 : sl + 1;
                }
            }
            if (!sec) PROFH(4);
}

#define PROF_PARAMS
#define PROF_ARGS
__device__ __noinline__ void helper_late(const Params& p, int r_, int j_, int warp_ PROF_PARAMS) {
    extern __shared__ __align__(1024) unsigned char smem[];
    const uint32_t sb = (uint32_t)__cvta_generic_to_shared(smem);
    const int r = opaque(r_), j = opaque(j_), warp = opaque(warp_), nq = j >> 1, b = 8 * r + j;
    uint32_t* const act = (uint32_t*)__shfl_sync(~0u, (unsigned long long)(p.actb + (size_t)r * RB_WORDS), 0);
    {
        const int lane = fresh_tid() & 31;
        const uint32_t target = lds1(sb + M_EPOCH) + 1;
        if (warp == 8) { expect_e(BAR(B_XCH), 14336); expect_e(BAR(B_XCH + 1), 14336); }
            if (warp == 9) {
#pragma unroll 1
                for (int kv = 0; kv < 2; kv++) {
                    mbar_wait(BAR(B_PUB + kv), 0);
                    wait_flags(g_flag + b * 128 + lane, target, (r >= 2 ? 6u : r == 1 ? 2u : 0u) << (8 * kv));
                    fence_async_global();
                    const uint32_t dst = sb + OFF_Y + (kv ? Y_VR : Y_K);
                    expect_e(BAR(B_KRFULL + kv), r >= 2 ? 28672 : r == 1 ? 14336 : 0);
                    if (r >= 2) bulk_e(dst, act - 2 * RB_WORDS + RB_KV + j * 7168 + kv * 3584, 14336, BAR(B_KRFULL + kv));
                    if (r >= 1) bulk_e(dst + 14336, act - RB_WORDS + RB_KV + j * 7168 + kv * 3584, 14336, BAR(B_KRFULL + kv));
                    if (kv == 0) { PROFH(8); }
                }
            } else if (warp == 8) {
                uint4 v[8];
                mbar_wait(BAR(B_WOFULL), 0);
#pragma unroll
                for (int k = 0; k < 8; k++) v[k] = ld_relaxed4(mod_src(lane + 32 * k, r, j, true));
#pragma unroll
                for (int k = 0; k < 8; k++) mod_store(sb, v[k], mod_src(lane + 32 * k, r, j, true), lane + 32 * k);
                warp_arrive(BAR(B_MOD1));
            } else if (warp == 11) {
                if (kh == 1 && r < 14) {
                    const uint32_t wmbuf = sb + OFF_X + HALF;
                    const int mcol = 2 * DM + 32 * (4 * r + nq);
                    mbar_wait(BAR(B_XFREE), 0);
                    tma3_e(wmbuf, &p.wm2, mcol, 0, 0, BAR(B_WMFULL));
                    tma3_e(wmbuf + 14336, &p.wm2, mcol, 224, 0, BAR(B_WMFULL));
#pragma unroll 1
                    for (int wd = lane; wd < 224; wd += 32) {
                        const uint32_t cb = __ldg((const uint32_t*)p.c + wd);
                        sts1(wmbuf + 28672 + (wd >> 3) * 32 + (wd & 3) * 8 + (wd & 4), pack2(silu_bf(cb & 0xFFFFu), silu_bf(cb >> 16)));
                    }
                    __syncwarp();
                    mbar_wait(BAR(B_WMFULL), 0);
                    const uint32_t wa = wmbuf + (8 * (lane >> 4) + (lane & 7)) * 64 + ((lane >> 3) & 1) * 16;
                    float d[2][4] = {};
#pragma unroll 4
                    for (int ks = 0; ks < 28; ks++) {
                        uint32_t A[8];
                        ldsm4t(wa + ks * 1024, A); ldsm4t(wa + ks * 1024 + 32, A + 4);
                        const float2 v = lds2f(wmbuf + 28672 + ks * 32 + (lane & 3) * 8);
                        mma16816(d[0], A[0], A[1], A[2], A[3], __float_as_uint(v.x), __float_as_uint(v.y));
                        mma16816(d[1], A[4], A[5], A[6], A[7], __float_as_uint(v.x), __float_as_uint(v.y));
                    }
                    const int q = lane & 3, col = mcol + 8 * q + (lane >> 2);
                    const uint32_t word = mod_word(q == 0 ? d[0][0] : q == 1 ? d[0][2] : q == 2 ? d[1][0] : d[1][2], col, target);
#pragma unroll
                    for (int i = 0; i < 8; i++) st_relaxed(g_mod + i * 6 * DM + col, word);
                }
                warp_arrive(BAR(B_WMFREE));
                mbar_wait(BAR(B_VRFULL), 0);
                l2_prefetch_e((const char*)p.wg + (size_t)b * 12544, 12544);
                l2_prefetch_e((const char*)p.wu + (size_t)b * 12544, 12544);
#pragma unroll 1
                for (int k = 0; k < (r < 12 ? 2 : 1); k++) {
                    const int u = 28 * kh + r + 16 * k;
                    expect_e(BAR(B_XFULL + k), 7168);
                    tma3_e(sb + OFF_Y + 102400, &p.dn, 0, 32 * u, 7 * j, BAR(B_XFULL + k));
                    tma3_e(sb + OFF_Y + 102400 + 3584, &p.dn, 0, 32 * u, 7 * (j ^ 1), BAR(B_XFULL + k));
                    mbar_wait(BAR(B_XFULL + k), 1);
                    asm volatile("{\n.reg .pred p;\nelect.sync _|p, 0xffffffff;\n@p cp.async.bulk.global.shared::cta.bulk_group [%0], [%1], 7168;\n"
                                 "cp.async.bulk.commit_group;\ncp.async.bulk.wait_group 0;\n}" ::"l"(g_wd + (size_t)(u * 4 + nq) * 1792), "r"(sb + OFF_Y + 102400) : "memory");
                    __syncwarp();
                }
                warp_arrive(BAR(B_FULLK));
                fence_gpu();
                if (lane < 16) st_relaxed(g_flag + (8 * lane + j) * 128 + 96 + r, target);
            }
        if (warp == 8 || warp == 11) {
            const int sec = warp == 11;
            if (sec) ring_loader<1>(p, sb, r, j, lane); else ring_loader<0>(p, sb, r, j, lane);
            mbar_wait(BAR(B_DONE), 0);
        } else if (warp == 9) {
#pragma unroll
            for (int ev = 0; ev < 4; ev++) { expect_e(BAR(B_GFULL + ev), ev < 2 ? HALF / 2 : 16384 + 4096); expect_e(BAR(B_XFULL + 2 + ev), ev < 2 ? HALF / 2 : HALF - 16384); }
            mbar_wait(BAR(B_PUB + 2), 0);
            const uint32_t* fp = g_flag + b * 128 + 32 + lane;
            const int par = (target - 1) & 1;
#pragma unroll 1
            for (int n = 0, ev = 0; ev < 4; n++) {
                if (ev == 1) mbar_wait(BAR(B_PUB + 3), 0);
                uint32_t ok = __ballot_sync(~0u, (int)(ld_relaxed(fp) - target) >= 0) >> (8 * ev);
                while ((ok & 0xFFu) == 0xFFu) {
                    if (ev == 1) mbar_wait(BAR(B_FULLK), 1);
                    asm volatile("fence.acquire.gpu;" ::: "memory");
                    fence_async_global();
                    const int tile = (ev & 1) + (ev >> 1) * par * 2;
                    const uint32_t dst = sb + (ev == 0 ? OFF_X : OFF_Y + (ev & 1) * HALF), first = ev < 2 ? HALF / 2 : 16384;
                    const char* src = (const char*)(act + RB_O + ((ev >> 1) * 2 + tile) * 14336);
                    if (ev >= 2) bulk_e(sb + OFF_X + X_STAT + (ev & 1) * 49152, act + RB_ST + tile * 1024, 4096, BAR(B_GFULL + ev));
                    bulk_e(dst, src, first, BAR(B_GFULL + ev));
                    bulk_e(dst + first, src + first, HALF - first, BAR(B_XFULL + 2 + ev));
                    if (ev) PROFH(4 + ev);
                    ev++; ok >>= 8;
                }
                if (n > SPIN_LIMIT) __trap();
            }
            mbar_wait(BAR(B_XFULL + 5), 1);
#pragma unroll 1
            for (int hf = 0; hf < 2; hf++) {
                const int tile = (par ^ 1) * 2 + hf;
                uint4* xz = (uint4*)(act + RB_X1 + tile * 14336 + j * 1792) + lane;
#pragma unroll
                for (int i = 0; i < 14; i++) xz[i * 32] = make_uint4(0, 0, 0, 0);
                ((uint4*)(act + RB_ST + (tile * 8 + j) * 128))[lane] = make_uint4(0, 0, 0, 0);
            }
#pragma unroll 1
            for (int ps = 0; ps < 3; ps++) {
                mbar_wait(BAR(B_PUB + 6 + ps), 0);
                wait_flags(g_flag + b * 128 + 64 + lane, target, (0x55u << kh) << (8 * ps));
                warp_arrive(BAR(B_HRDY + ps));
                PROFH(9 + ps);
            }
        } else {
#pragma unroll 1
            for (int k = 0; k < 9; k++) {
                uint32_t* fp = k < 2 ? g_flag + (b + 8 * lane) * 128 + k * 8 + lane : g_flag + (8 * r + lane) * 128 + 16 + k * 8 + j;
                mbar_wait(BAR(B_PUB + k), 0);
                if (k != 4 && k != 5) fence_gpu();
                if (k < 2 ? (lane == 1 || lane == 2) : lane < 8) st_relaxed(fp, target);
                if (k >= 3 && k <= 5) PROFH(k - 3);
            }
        }
    }
}

__global__ void __cluster_dims__(2, 1, 1) __launch_bounds__(384, 1) fused_block_kernel(const __grid_constant__ Params p) {
    extern __shared__ __align__(1024) unsigned char smem[];
    const uint32_t sb = (uint32_t)__cvta_generic_to_shared(smem);
    const int tid = threadIdx.x, lane = tid & 31, warp = __shfl_sync(~0u, tid >> 5, 0);
    const int m = blockIdx.x >> 1;
    int r, nq;
    if (m < 4) { r = 15; nq = m; }
    else if (m < 36) { r = (m - 4) & 7; nq = (m - 4) >> 3; }
    else { nq = (m - 36) / 7; r = m - 28 - 7 * nq; }
    const int j = opaque(2 * nq + (blockIdx.x & 1)), b = 8 * r + j, fs = 4 * kh + nq;
#define act (p.actb + (size_t)r * RB_WORDS)
    constexpr uint32_t sc = 0;
    if (lane == 0 && warp < 9 && warp != 6 && warp != 7) {
        const int i0 = warp == 8 ? 0 : 8 + 8 * warp, cnt = warp == 0 || warp == 8 ? 1 : warp < 3 ? 2 : 8;
#pragma unroll
        for (int k = 0; k < 8; k++) if (i0 + k != B_WMFULL) mbar_init(BAR(i0 + k), cnt);
        if (warp == 8) mbar_init(BAR(B_WMFULL), 1);
        asm volatile("fence.mbarrier_init.release.cluster;" ::: "memory");
        fence_async_smem();
    }

    if (warp >= 8) {
        const int lane = fresh_tid() & 31;
        const bool early = kh == 0, gemv = r < 14;
        const int mcol = early ? 16 * (4 * r + nq) : 2 * DM + 32 * (4 * r + nq);
        const uint32_t wmbuf = sb + OFF_Y + HALF;
        if (warp == 8) {
            __syncwarp();
            expect_e(BAR(B_WMFULL), gemv ? 28672 >> early : 0);
            if (early && gemv) { tma3_e(wmbuf, &p.wm, mcol, 0, 0, BAR(B_WMFULL)); tma3_e(wmbuf + 7168, &p.wm, mcol, 224, 0, BAR(B_WMFULL)); }
#pragma unroll
            for (int kb = 0; kb < XFIRST; kb++) {
                expect_e(BAR(B_XFULL + kb), 16384);
                tma3_e(sb + OFF_X + kb * 16384, &p.xm, 64 * kb, 128 * r, 0, BAR(B_XFULL + kb));
            }
        }
        asm volatile("setmaxnreg.dec.sync.aligned.u32 56;");
        if (warp == 9) {
#pragma unroll
            for (int i = 56; i < 64; i++) init_e(BAR(i), 1);
            fence_async_smem();
        }
        bar_arrive(0, 384);
        asm volatile("barrier.cluster.arrive.relaxed.aligned;" ::: "memory");
        if (warp == 8) {
#pragma unroll
            for (int kb = XFIRST; kb < 7; kb++) {
                expect_e(BAR(B_XFULL + kb), 16384);
                tma3_e(sb + OFF_X + kb * 16384, &p.xm, 64 * kb, 128 * r, 0, BAR(B_XFULL + kb));
            }
            if (KDELAY >= 0) { mbar_wait(BAR(B_XFULL + KDELAY), 0); l2_prefetch_e((const char*)p.wqkv + (size_t)b * 9408, 9408); }
#pragma unroll 1
            for (int mt = 0; mt < 4; mt++) {
                if (mt == 1) bar_sync(9, 384);
                if (mt == 3) mbar_wait(BAR(B_WMFREE), 0);
                if (mt) mbar_wait(BAR(mt == 1 ? B_MOD1 : mt == 2 ? B_XFREE : B_VRFULL), 0);
                const uint32_t bar = BAR(mt == 3 ? B_WOFULL : B_FULLK + mt), dst = sb + (mt < 2 ? OFF_Y : OFF_X) + (mt & 1) * HALF;
                const int c0 = (mt < 2 ? DM + DM * mt : 0) + 56 * j - 8 * kh;
                if (!sc) {
                    expect_e(bar, HALF);
                    tma3_e(dst, mt == 3 ? &p.wo : &p.qkv, c0, 0, 0, bar);
                    tma3_e(dst + HALF / 2, mt == 3 ? &p.wo : &p.qkv, c0, 224, 0, bar);
                }
            }
        } else {
            if (KDELAY < 0 && warp == 10) l2_prefetch_e((const char*)p.wqkv + (size_t)b * 9408, 9408);
            bar_sync(9, 384);
            if (sc) return;
            if (warp == 11 && early) {
                const uint32_t target = lds1(sb + M_EPOCH) + 1;
                mbar_wait(BAR(B_GEMV), 0);
                float sum = 0.f;
#pragma unroll
                for (int i = 0; i < 8; i++) sum += *(const float*)(smem + OFF_Y + HALF + 29696 + (i * 16 + (lane & 15)) * 4);
                uint32_t* mg = g_mod + mcol + (lane & 15) + (lane >> 4) * 4 * 6 * DM;
                const uint32_t word = mod_word(sum, mcol, target);
                if (gemv) { st_relaxed(mg, word); st_relaxed(mg + 6 * DM, word); st_relaxed(mg + 12 * DM, word); st_relaxed(mg + 18 * DM, word); }
            }
        }
    }
    if (LIKELY(warp < 8)) {
        const int w = warp >> 2, wi = warp & 3;
#define COORDS const int t = fresh_tid() & 127, lane = t & 31, q = lane & 3, lr = lane >> 2, ra = 64 * w + 16 * wi + lr; \
        const uint32_t lx = (lane >> 4) ^ (lane & 7), mrow = (64 * w + 16 * wi + ((lane >> 3) & 1) * 8 + (lane & 7)) * 128; \
        (void)q; (void)lr; (void)ra; (void)lx; (void)mrow;
        const int sid = 2 * (j & 3) + w;
#define RUN(k) (!sc || sid == (k))
#define WAIT(i, par) mbar_wait_c(BAR(i), (par) | sc)
        constexpr uint64_t DB128 = dconst(4096, 1024, 1);
        {
            const int wd = fresh_tid();
            const uint32_t cb = wd < 224 ? __ldg((const uint32_t*)p.c + wd) : 0u;
            if (wd == 255 && !sc) sts1(sb + M_EPOCH, atomicAdd(&g_ticket, 1u) / NCTA);
            sts1(sb + OFF_Y + HALF + 28672 + (wd >> 3) * 32 + (wd & 3) * 8 + (wd & 4), pack2(silu_bf(cb & 0xFFFFu), silu_bf(cb >> 16)));
        }
        bar_arrive(9, 384);
        bar_sync(0, 384);
        asm volatile("barrier.cluster.arrive.relaxed.aligned;" ::: "memory");
        asm volatile("setmaxnreg.inc.sync.aligned.u32 224;");
        PROFC(0);
        uint32_t xr[16];
        {
            COORDS
            uint32_t h[112];
            uint32_t ra2, na2, rb2, nb2;
            const int mi = min(128 * w + t, 223);
            const uint4* msrc = mod_src(mi, r, j, false);
            uint4 mv;
            {
                float ds[4] = {}, da[2][4] = {}, db[2][4] = {};
                const uint32_t ONE2 = 0x3F803F80u;
#pragma unroll
                for (int kb = 0; kb < 7; kb++) {
                    if (kb == GEMV_AT && kh == 0) { WAIT(B_WMFULL, 0); gemv_part(sb + OFF_Y + HALF, warp, lane); warp_arrive(BAR(B_GEMV)); }
                    WAIT(B_XFULL + kb, 0);
#pragma unroll
                    for (int k4 = 0; k4 < 4; k4++) ldsm4(sb + OFF_X + mrow + kb * 16384 + (((2 * k4) ^ lx) << 4), h + 16 * kb + 4 * k4);
#pragma unroll
                    for (int k4 = 0; k4 < 4; k4++) {
                        const uint32_t* f = h + 16 * kb + 4 * k4;
                        mma16816(ds, f[0], f[1], f[2], f[3], ONE2, ONE2);
                        mma1688(da[0], f[0], f[1], f[0]); mma1688(db[0], f[0], f[1], f[1]);
                        mma1688(da[1], f[2], f[3], f[2]); mma1688(db[1], f[2], f[3], f[3]);
                    }
                }
#pragma unroll
                for (int i = 0; i < 4; i++) {
                    const int ch = 7 * j + 2 * i + (lane >> 4);
                    ldsm4(sb + OFF_X + mrow + (ch >> 3) * 16384 + (((ch ^ lane) & 7) << 4), xr + 4 * i);
                }
                mv = ld_relaxed4(msrc);
                warp_arrive(BAR(B_XFREE));
                float qa = (lr & 1) ? da[0][1] + da[1][1] : da[0][0] + da[1][0];
                float qb = (lr & 1) ? db[0][3] + db[1][3] : db[0][2] + db[1][2];
                const int src = (lane & ~3) | (lr >> 1);
                qa = __shfl_sync(~0u, qa, src);
                qb = __shfl_sync(~0u, qb, src);
                ln_coeffs(ds[0] * (1.f / DM), qa * (1.f / DM), ra2, na2);
                ln_coeffs(ds[2] * (1.f / DM), qb * (1.f / DM), rb2, nb2);
#pragma unroll
                for (int i = 0; i < 4 * NPRE; i += 2) { h[i] = hfma2(h[i], ra2, na2); h[i + 1] = hfma2(h[i + 1], rb2, nb2); }
            }
            PROFC(1);
            {
                float ak[28], av[28], aq[28];
                uint32_t kp[14], vp[14];
                const uint64_t bq0 = (DB128 & ~0xFFFFFFFFull) | (mkdesc(sb + OFF_X, DB128) + kh), bk0 = bq0 + (OFF_Y >> 4), bv0 = bk0 + (HALF >> 4);
                uint32_t* kvg = act + RB_KV + j * 7168 + (8 * w + 2 * wi) * 224 + lane;
                mod_store(sb, mv, msrc, mi);
                bar_sync(3, 256);
                if (warp == 0) warp_arrive(BAR(B_MOD1));
                WAIT(B_FULLK, 0);
                PROFC(2);
                reg_def<28>(ak);
#pragma unroll
                for (int g4 = 0; g4 < 4; g4++) {
#pragma unroll
                    for (int ks = 7 * g4; ks < 7 * g4 + 7; ks++) {
                        const uint4 st = *(const uint4*)(smem + M_ST + ks * 64 + q * 16);
                        if (ks >= NPRE) {
                            h[4 * ks] = hfma2(h[4 * ks], ra2, na2); h[4 * ks + 1] = hfma2(h[4 * ks + 1], rb2, nb2);
                            h[4 * ks + 2] = hfma2(h[4 * ks + 2], ra2, na2); h[4 * ks + 3] = hfma2(h[4 * ks + 3], rb2, nb2);
                        }
                        h[4 * ks] = hfma2(h[4 * ks], st.x, st.y); h[4 * ks + 1] = hfma2(h[4 * ks + 1], st.x, st.y);
                        h[4 * ks + 2] = hfma2(h[4 * ks + 2], st.z, st.w); h[4 * ks + 3] = hfma2(h[4 * ks + 3], st.z, st.w);
                    }
                    WG_FENCE();
#pragma unroll
                    for (int ks = 7 * g4; ks < 7 * g4 + 7; ks++) wgmma_rl_56(ak, h[4 * ks], h[4 * ks + 1], h[4 * ks + 2], h[4 * ks + 3], bk0 + ks * 128, ks != 0);
                }
                WG_COMMIT();
                PROFC(3);
                reg_def<28>(av);
                WG_WAIT(0);
                reg_fence<28>(ak);
#pragma unroll
                for (int g = 0; g < 7; g++) {
                    kp[2 * g] = pack2(ak[4 * g], ak[4 * g + 1]); kp[2 * g + 1] = pack2(ak[4 * g + 2], ak[4 * g + 3]);
                    kvg[g * 32] = kp[2 * g]; kvg[224 + g * 32] = kp[2 * g + 1];
                }
                warp_arrive(BAR(B_PUB));
                PROFC(4);
                if (KEARLY) WAIT(B_FULLV, 0);
                WG_FENCE();
#pragma unroll
                for (int ks = KEARLY ? 0 : 8; ks < 28; ks++) wgmma_rl_56(av, h[4 * ks], h[4 * ks + 1], h[4 * ks + 2], h[4 * ks + 3], bv0 + ks * 128, ks != 0);
                WG_COMMIT();
                WAIT(B_FULLQ, 0);
                reg_def<28>(aq);
                WG_FENCE();
#pragma unroll
                for (int ks = 0; ks < 8; ks++) wgmma_rl_56(aq, h[4 * ks], h[4 * ks + 1], h[4 * ks + 2], h[4 * ks + 3], bq0 + ks * 128, ks != 0);
                WG_COMMIT();
                WG_WAIT(1);
                reg_fence<28>(av);
#pragma unroll
                for (int g = 0; g < 7; g++) {
                    vp[2 * g] = pack2(av[4 * g], av[4 * g + 1]); vp[2 * g + 1] = pack2(av[4 * g + 2], av[4 * g + 3]);
                    kvg[3584 + g * 32] = vp[2 * g]; kvg[3584 + 224 + g * 32] = vp[2 * g + 1];
                }
                warp_arrive(BAR(B_PUB + 1));
                PROFC(5);
                WG_FENCE();
#pragma unroll
                for (int ks = 8; ks < 28; ks++) wgmma_rl_56(aq, h[4 * ks], h[4 * ks + 1], h[4 * ks + 2], h[4 * ks + 3], bq0 + ks * 128, 1);
                WG_COMMIT();
                WAIT(B_PUB + 1, 0);
                const uint32_t rg = 8 * w + 2 * wi + ((lane >> 3) & 1);
                const uint32_t ko = sb + OFF_Y + Y_KOWN + rg * 896 + (lane & 7) * 16, qo = sb + OFF_Y + Y_Q + rg * 1024 + (lane >> 4) * 128 + (lane & 7) * 16;
#pragma unroll
                for (int g = 0; g < 6; g += 2) {
                    stsm4(ko + (g + (lane >> 4)) * 128, kp[2 * g], kp[2 * g + 1], kp[2 * g + 2], kp[2 * g + 3]);
                    stsm4(ko + (Y_VOWN - Y_KOWN) + (g + (lane >> 4)) * 128, vp[2 * g], vp[2 * g + 1], vp[2 * g + 2], vp[2 * g + 3]);
                }
                stsm4(ko + (lane >> 4) * (Y_VOWN - Y_KOWN) + 6 * 128, kp[12], kp[13], vp[12], vp[13]);
                WG_WAIT(0);
                reg_fence<28>(aq);
                __syncwarp();
                if (lane < 3 && w == 1) mbar_arrive(BAR(B_EMPTY + lane));
                uint32_t qp[14];
#pragma unroll
                for (int i = 0; i < 14; i++) qp[i] = pack2(aq[2 * i], aq[2 * i + 1]);
                stsm4(qo, qp[0], qp[1], qp[2], qp[3]);
                stsm4(qo + 256, qp[4], qp[5], q < 2 ? qp[6] : 0u, q < 2 ? qp[7] : 0u);
                stsm4(qo + 512, q < 2 ? 0u : qp[6], q < 2 ? 0u : qp[7], qp[8], qp[9]);
                stsm4(qo + 768, qp[10], qp[11], qp[12], qp[13]);
                fence_async_smem();
                if (!sc) bar_sync(3, 256);
            }
        }
        PROFC(6);
        WAIT(B_KRFULL, 0);
        if (ATT_OFF && w == ATT_WG) { const uint32_t t0 = clock(); while (clock() - t0 < ATT_OFF) {} }
        PROFC(7);
        if (RUN(2)) {
#pragma unroll 1
            for (int hf = sc; hf < 2; hf++) {
                COORDS
                float s[160];
                const float CS = 0.18898223650461361f * 1.4426950408889634f;
                const float NEG = __int_as_float(0xFF800000);
                constexpr uint64_t DQ = dconst(128, 1024, 0), DK = dconst(128, 896, 0);
                {
                    const uint32_t qd = mkdesc(sb + OFF_Y + Y_Q + hf * 8192 + w * 512, DQ), kd = mkdesc(sb + OFF_Y + Y_K + hf * 8 * 896 + w * 384, DK);
                    reg_def<160>(s);
                    WG_FENCE();
                    wgmma_sk_160<DQ, DK>(s, qd, kd, 0);
                    wgmma_sk_160<DQ, DK>(s, qd + 16, kd + 16, 1);
                    wgmma_sk_160<DQ, DK>(s + 80, qd, kd + 20 * 56, 0);
                    wgmma_sk_160<DQ, DK>(s + 80, qd + 16, kd + 20 * 56 + 16, 1);
                    WG_COMMIT();
                    WG_WAIT(0);
                    reg_fence<160>(s);
                }
                if (r < 2) {
                    const int pmin = 4 - 2 * r - hf;
#pragma unroll
                    for (int p4 = 0; p4 < 4; p4++)
                        if (p4 < pmin) {
#pragma unroll
                            for (int i = 0; i < 32; i++) asm volatile("mov.b32 %0, 0xFF800000;" : "=f"(s[32 * p4 + i]));
                        }
                }
                const bool c0 = 2 * q > lr, c1 = 2 * q + 1 > lr;
#pragma unroll
                for (int pp = 0; pp < 4; pp++) {
                    const bool me = pp == wi;
                    float* e = s + 8 * pp;
                    if (me && !c0) { e[0] = NEG; e[6] = NEG; }
                    if (me && !c1) { e[1] = NEG; e[7] = NEG; }
                    if (me) { e[2] = NEG; e[3] = NEG; }
                    e = s + 8 * (pp + 16);
                    if (me && c0) { e[0] = NEG; e[6] = NEG; }
                    if (me && c1) { e[1] = NEG; e[7] = NEG; }
                    if (me) { e[4] = NEG; e[5] = NEG; }
                }
#pragma unroll
                for (int i = 0; i < 24; i++) s[i] = (i >> 3) < wi ? s[136 + i] : s[i];
                int i0 = 0x80000000, i1 = 0x80000000, i2 = 0x80000000, i3 = 0x80000000;
#pragma unroll
                for (int pp = 0; pp < 17; pp++) {
                    const float* e = s + 8 * pp;
                    i0 = __vimax3_s32(i0, __float_as_int(e[0]), __float_as_int(e[1])); i1 = __vimax3_s32(i1, __float_as_int(e[2]), __float_as_int(e[3]));
                    i2 = __vimax3_s32(i2, __float_as_int(e[4]), __float_as_int(e[5])); i3 = __vimax3_s32(i3, __float_as_int(e[6]), __float_as_int(e[7]));
                }
                i0 = max(i0, i2); i1 = max(i1, i3);
                i0 = max(i0, __shfl_xor_sync(~0u, i0, 1)); i1 = max(i1, __shfl_xor_sync(~0u, i1, 1));
                i0 = max(i0, __shfl_xor_sync(~0u, i0, 2)); i1 = max(i1, __shfl_xor_sync(~0u, i1, 2));
                if (__any_sync(~0u, (i0 | i1) < 0)) {
                    uint32_t u0 = ~0u, u1 = ~0u, u2 = ~0u, u3 = ~0u;
#pragma unroll
                    for (int pp = 0; pp < 17; pp++) {
                        const float* e = s + 8 * pp;
                        u0 = __vimin3_u32(u0, __float_as_uint(e[0]), __float_as_uint(e[1])); u1 = __vimin3_u32(u1, __float_as_uint(e[2]), __float_as_uint(e[3]));
                        u2 = __vimin3_u32(u2, __float_as_uint(e[4]), __float_as_uint(e[5])); u3 = __vimin3_u32(u3, __float_as_uint(e[6]), __float_as_uint(e[7]));
                    }
                    u0 = min(u0, u2); u1 = min(u1, u3);
                    u0 = min(u0, __shfl_xor_sync(~0u, u0, 1)); u1 = min(u1, __shfl_xor_sync(~0u, u1, 1));
                    u0 = min(u0, __shfl_xor_sync(~0u, u0, 2)); u1 = min(u1, __shfl_xor_sync(~0u, u1, 2));
                    if (i0 < 0) i0 = u0;
                    if (i1 < 0) i1 = u1;
                }
                const float ma = __int_as_float(i0), mb = __int_as_float(i1);
                const float na = -ma * CS, nb = -mb * CS;
                PROFC(8 + 3 * hf);
                {
                    WAIT(B_VRFULL, 0);
                    float o[16] = {}, rs[4] = {};
                    const uint32_t va = sb + OFF_Y + Y_VR + (8 * hf + ((lane >> 3) & 1)) * 896 + (3 * w + (lane >> 4)) * 128 + (lane & 7) * 16;
                    constexpr uint32_t OWN = Y_VOWN - 32 * 896;
#pragma unroll
                    for (int pp = 0; pp < 17; pp++) {
                        uint32_t B[8];
                        const uint32_t v = va + pp * 1792 + (pp < 3 ? (pp < wi ? 17 * 1792 + OWN : 0) : pp == 16 ? OWN : pp >= 12 ? hf * OWN : 0);
                        ldsm4t(v, B); ldsm4t(v + 256, B + 4);
                        float e[8];
#pragma unroll
                        for (int i = 0; i < 8; i++) e[i] = ex2(fmaf(s[8 * pp + i], CS, (i & 2) ? nb : na));
                        const uint32_t p0 = pack2(e[0], e[1]), p1 = pack2(e[2], e[3]), p2 = pack2(e[4], e[5]), p3 = pack2(e[6], e[7]);
                        mma16816(rs, p0, p1, p2, p3, 0x3F803F80u, 0x3F803F80u);
#pragma unroll
                        for (int g = 0; g < 4; g++) mma16816(o + 4 * g, p0, p1, p2, p3, B[2 * g], B[2 * g + 1]);
                    }
                    PROFC(9 + 3 * hf);
                    const float ia = rcp(rs[0]), ib = rcp(rs[2]);
                    uint32_t* og = act + RB_O + hf * 14336 + (7 * j + 3 * w) * 256 + wi * 64 + lane;
#pragma unroll
                    for (int g = 0; g < 4; g++) {
                        if ((g == 3 - 3 * w) ? ((q >> 1) == w) : true) {
                            og[g * 256] = pack2(o[4 * g] * ia, o[4 * g + 1] * ia);
                            og[g * 256 + 32] = pack2(o[4 * g + 2] * ib, o[4 * g + 3] * ib);
                        }
                    }
                    warp_arrive(BAR(B_PUB + 2 + hf));
                    PROFC(10 + 3 * hf);
                }
            }
        }
        uint32_t x1p[14];
        COORDS
        constexpr uint64_t DT = dconst(1024, 128, 0);
        const int tile = opaque((lds1(sb + M_EPOCH) & 1) * 2 + w);
        if (RUN(4)) {
            float ac[28];
            const uint32_t ad = mkdesc(sb + (w ? OFF_Y + HALF : OFF_X), DT), bd = mkdesc(sb + OFF_X + HALF, DB128) + kh;
            WAIT(B_WOFULL, 0);
            WAIT(B_MOD1, 1);
            WAIT(B_GFULL + w, 0);
            PROFC(28);
            reg_def<28>(ac);
#pragma unroll 1
            for (int u = 0; u < 4; u++) {
                if (u == 2) WAIT(B_XFULL + 2 + w, 1);
                WG_FENCE();
#pragma unroll
                for (int i = 0; i < 7; i++) wgmma_ss_56<DT, DB128>(ac, ad + (7 * u + i) * 128, bd + (7 * u + i) * 128, (u | i) != 0);
            }
            WG_COMMIT();
            WG_WAIT(0);
            reg_fence<28>(ac);
            PROFC(14);
            __syncwarp();
            if (lane < 3) mbar_arrive(BAR(B_EMPTY + 4 - w + lane));
            if (lane < 3 && w == 0) mbar_arrive(BAR(B_EMPTY + lane));
            float ds[4] = {}, da[4] = {}, db[4] = {};
            uint32_t* xo = act + RB_X1 + tile * 14336 + 7 * j * 256 + wi * 64 + lane;
#pragma unroll
            for (int g = 0; g < 7; g++) {
                const float2 ga = *(const float2*)(smem + M_G + (8 * g + 2 * q) * 4);
                x1p[2 * g] = pack2(fmaf(ga.x, ac[4 * g], bf_lo(xr[2 * g])), fmaf(ga.y, ac[4 * g + 1], bf_hi(xr[2 * g])));
                x1p[2 * g + 1] = pack2(fmaf(ga.x, ac[4 * g + 2], bf_lo(xr[2 * g + 1])), fmaf(ga.y, ac[4 * g + 3], bf_hi(xr[2 * g + 1])));
                st_relaxed(xo + g * 256, nz(x1p[2 * g])); st_relaxed(xo + g * 256 + 32, nz(x1p[2 * g + 1]));
                mma1688(ds, x1p[2 * g], x1p[2 * g + 1], 0x3F803F80u);
                mma1688(da, x1p[2 * g], x1p[2 * g + 1], x1p[2 * g]);
                mma1688(db, x1p[2 * g], x1p[2 * g + 1], x1p[2 * g + 1]);
            }
            const int src = (lane & ~3) | (lr >> 1);
            const float qa = __shfl_sync(~0u, (lr & 1) ? da[1] : da[0], src), qb = __shfl_sync(~0u, (lr & 1) ? db[3] : db[2], src);
            const float kk = (q & 1) ? ((q & 2) ? qb : qa) : ((q & 2) ? ds[2] : ds[0]);
            st_relaxed(act + RB_ST + ((tile * 8 + j) * 64 + 16 * wi + lr + 4 * (q & 2)) * 2 + (q & 1), nz(__float_as_uint(kk)));
            __syncwarp();
            if (lane < 2) mbar_arrive(BAR(B_PUB + 4 + w));
        } else reg_def<14>(x1p);
        PROFC(15);
        uint32_t h2a[32], h2b[24];
        {
            const int fa = pass_f(fs, 0), fb = pass_f(fs, 1), fc = pass_f(fs, 2);
            uint32_t* h2g = act + RB_H2 + (8 * w + 2 * wi) * 32 + lane;
            const uint32_t a0 = mkdesc(sb + OFF_Y + w * HALF, DT);
            if (RUN(3)) {
                uint32_t ra2, na2, rb2, nb2;
                {
                    const uint32_t* sg = act + RB_ST + ((tile * 8 + 2 * q) * 64 + 16 * wi + lr) * 2;
                    uint2 u[4];
                    WAIT(B_GFULL + 2 + w, 0);
                    PROFC(16);
#pragma unroll
                    for (int i = 0; i < 4; i++) { const float2 v = lds2f(sb + OFF_X + X_STAT + w * 49152 + ((2 * q + (i >> 1)) * 64 + 16 * wi + lr + 8 * (i & 1)) * 8); u[i] = make_uint2(__float_as_uint(v.x), __float_as_uint(v.y)); }
                    while (__any_sync(~0u, min(min(min(u[0].x, u[0].y), min(u[1].x, u[1].y)), min(min(u[2].x, u[2].y), min(u[3].x, u[3].y))) < 1u - sc)) {
#pragma unroll
                        for (int i = 0; i < 4; i++) u[i] = ld_relaxed2(sg + (i >> 1) * 128 + (i & 1) * 16);
                    }
                    warp_arrive(BAR(B_EMPTY + 3 + 3 * w));
                    float v[4] = {__uint_as_float(u[0].x) + __uint_as_float(u[2].x), __uint_as_float(u[0].y) + __uint_as_float(u[2].y),
                                  __uint_as_float(u[1].x) + __uint_as_float(u[3].x), __uint_as_float(u[1].y) + __uint_as_float(u[3].y)};
#pragma unroll
                    for (int i = 0; i < 4; i++) { v[i] += __shfl_xor_sync(~0u, v[i], 1); v[i] += __shfl_xor_sync(~0u, v[i], 2); }
                    ln_coeffs(v[0] * (1.f / DM), v[1] * (1.f / DM), ra2, na2);
                    ln_coeffs(v[2] * (1.f / DM), v[3] * (1.f / DM), rb2, nb2);
                }
                const uint32_t ha = sb + OFF_Y + w * HALF + (lane >> 4) * 1024 + (2 * wi + ((lane >> 3) & 1)) * 128 + (lane & 7) * 16;
                const uint32_t sta = sb + M_ST + q * 16;
                const uint32_t* xg = act + RB_X1 + tile * 14336 + (lane >> 4) * 256 + wi * 64 + (lane & 15) * 4;
                uint32_t x[8];
                const uint32_t xs = sb + OFF_Y + w * HALF + (lane >> 4) * 1024 + wi * 256 + (lane & 15) * 16;
                uint4 st[2];
                auto load = [&](int s) {
                    if (s == 4) mbar_wait_c(BAR(B_XFULL + 4 + w), 1);
                    ldsm4(ha + s * 4096, x); ldsm4(ha + s * 4096 + 2048, x + 4);
                    st[0] = lds4(sta + s * 128); st[1] = lds4(sta + s * 128 + 64);
                };
                auto prep = [&](int s, uint32_t* f) {
                    if (__any_sync(~0u, min(min(min(x[0], x[1]), min(x[2], x[3])), min(min(x[4], x[5]), min(x[6], x[7]))) < 1u - sc)) {
                        WG_WAIT(0);
                        x1_fix(xg, xs, s);
                        ldsm4(ha + s * 4096, x); ldsm4(ha + s * 4096 + 2048, x + 4);
                    }
#pragma unroll
                    for (int i = 0; i < 2; i++) {
                        f[4 * i] = hfma2(hfma2(x[4 * i], ra2, na2), st[i].x, st[i].y); f[4 * i + 1] = hfma2(hfma2(x[4 * i + 1], rb2, nb2), st[i].x, st[i].y);
                        f[4 * i + 2] = hfma2(hfma2(x[4 * i + 2], ra2, na2), st[i].z, st[i].w); f[4 * i + 3] = hfma2(hfma2(x[4 * i + 3], rb2, nb2), st[i].z, st[i].w);
                    }
                    if (s < 13) load(s + 1);
                    stsm4(ha + s * 4096, f[0], f[1], f[2], f[3]); stsm4(ha + s * 4096 + 2048, f[4], f[5], f[6], f[7]);
                };
                float ac[128];
                uint32_t fr[3][8];
                uint64_t bd = (DB128 & ~0xFFFFFFFFull) | mkdesc(sb, DB128);
                reg_def<128>(ac);
                load(0);
                prep(0, fr[0]);
                PROFC(17);
#pragma unroll
                for (int s = 0; s < 14; s++) {
                    const uint32_t* f = fr[s % 3];
                    WAIT(B_FULL + g1_slot(s), s >= 7);
                    WG_FENCE();
                    wgmma_rl_256(ac, f[0], f[1], f[2], f[3], bd, s != 0);
                    wgmma_rl_256(ac, f[4], f[5], f[6], f[7], bd + 128, 1);
                    bd += s == 6 ? p.zero - 6 * 1024ull : 1024;
                    WG_COMMIT();
                    if (s < 13) prep(s + 1, fr[(s + 1) % 3]);
                    if (s > 0) { WG_WAIT(1); warp_arrive(BAR(B_EMPTY + g1_slot(s - 1))); }
                }
                fence_async_smem();
                PROFC(18);
                WG_WAIT(0);
                reg_fence<128>(ac);
                warp_arrive(BAR(B_EMPTY + 6));
#pragma unroll
                for (int g = 0; g < 16; g++) {
                    h2a[2 * g] = hmul2(pack2_relu(ac[4 * g], ac[4 * g + 1]), pack2(ac[64 + 4 * g], ac[64 + 4 * g + 1]));
                    h2a[2 * g + 1] = hmul2(pack2_relu(ac[4 * g + 2], ac[4 * g + 3]), pack2(ac[64 + 4 * g + 2], ac[64 + 4 * g + 3]));
                }
                bar_sync(1 + w, 128);
            } else reg_def<32>(h2a);
            PROFC(19);
            if (RUN(5)) {
                float ac[64];
                reg_def<64>(ac);
                const uint32_t bx = mkdesc(sb, dconst(8192, 1024, 1));
#pragma unroll kB
                for (int s = 0; s < 7; s++) {
                    WAIT(B_FULL + s, 0);
                    const uint32_t ad = a0 + s * 512, bd = bx + (slot_off(s) >> 4);
                    WG_FENCE();
#pragma unroll
                    for (int k = 0; k < 4; k++) wgmma_ss_128<DT, DB128>(ac, ad + k * 128, bd + k * 128, (s | k) != 0);
                    WG_COMMIT();
                    if (s == 1) {
#pragma unroll
                        for (int g = 0; g < 16; g++) { h2g[(fa / 8 + g) * 512] = h2a[2 * g]; h2g[(fa / 8 + g) * 512 + 32] = h2a[2 * g + 1]; }
                        warp_arrive(BAR(B_PUB + 6));
                    }
                    if (s > 0) { WG_WAIT(1); warp_arrive(BAR(B_EMPTY + s - 1)); }
                }
                WG_WAIT(0);
                reg_fence<64>(ac);
                warp_arrive(BAR(B_EMPTY + 6));
#pragma unroll
                for (int g = 0; g < 8; g++) {
                    h2b[2 * g] = hmul2(pack2_relu(ac[4 * g], ac[4 * g + 1]), pack2(ac[32 + 4 * g], ac[32 + 4 * g + 1]));
                    h2b[2 * g + 1] = hmul2(pack2_relu(ac[4 * g + 2], ac[4 * g + 3]), pack2(ac[32 + 4 * g + 2], ac[32 + 4 * g + 3]));
                }
            } else reg_def<16>(h2b);
            PROFC(27);
            if (RUN(6)) {
                float ac[32];
                reg_def<32>(ac);
                const uint32_t bx = mkdesc(sb, dconst(4096, 512, 2));
#pragma unroll kC
                for (int s = 0; s < 7; s++) {
                    WAIT(B_FULL + s, 1);
                    const uint32_t ad = a0 + s * 512, bd = bx + (slot_off(s) >> 4);
                    WG_FENCE();
#pragma unroll
                    for (int k = 0; k < 4; k++) wgmma_ss_64<DT, dconst(4096, 512, 2)>(ac, ad + k * 128, bd + k * 64, (s | k) != 0);
                    WG_COMMIT();
                    if (s == 1) {
#pragma unroll
                        for (int g = 0; g < 8; g++) { h2g[(fb / 8 + g) * 512] = h2b[2 * g]; h2g[(fb / 8 + g) * 512 + 32] = h2b[2 * g + 1]; }
                        warp_arrive(BAR(B_PUB + 7));
                    }
                    if (s > 0) { WG_WAIT(1); warp_arrive(BAR(B_EMPTY + s - 1)); }
                }
                WG_WAIT(0);
                reg_fence<32>(ac);
                __syncwarp();
                if (lane < 6) mbar_arrive(BAR(B_EMPTY + 6 + lane));
                PROFC(20);
#pragma unroll
                for (int g = 0; g < 4; g++) {
                    h2b[16 + 2 * g] = hmul2(pack2_relu(ac[4 * g], ac[4 * g + 1]), pack2(ac[16 + 4 * g], ac[16 + 4 * g + 1]));
                    h2b[16 + 2 * g + 1] = hmul2(pack2_relu(ac[4 * g + 2], ac[4 * g + 3]), pack2(ac[16 + 4 * g + 2], ac[16 + 4 * g + 3]));
                    h2g[(fc / 8 + g) * 512] = h2b[16 + 2 * g]; h2g[(fc / 8 + g) * 512 + 32] = h2b[16 + 2 * g + 1];
                }
                warp_arrive(BAR(B_PUB + 8));
                asm volatile("barrier.cluster.wait.aligned;" ::: "memory");
                if (lane == 0 && !sc) {
                    uint32_t rb;
                    asm volatile("mapa.shared::cluster.u32 %0, %1, %2;" : "=r"(rb) : "r"(BAR(B_PEER)), "r"(kh ^ 1));
                    asm volatile("mbarrier.arrive.relaxed.cluster.shared::cluster.b64 _, [%0];" ::"r"(rb) : "memory");
                }
            } else reg_def<8>(h2b + 16);
        }
        PROFC(21);
        if (RUN(7)) {
            float ac[56];
            reg_def<56>(ac);
            constexpr uint64_t DAN = dconst(2048, 128, 0);
            constexpr uint64_t DW = dconst(128, 512, 0);
            const uint32_t bx = mkdesc(sb, DW);
#pragma unroll
            for (int e = 0; e < 4; e++) {
                WAIT(B_FULL + e, 0);
                const uint64_t bd = ((DW & ~0xFFFFFFFFull) | bx) + (slot_off(e) >> 4);
                const uint32_t* hh = e < 2 ? h2a + 16 * e : h2b + 16 * (e - 2);
                WG_FENCE();
#pragma unroll
                for (int k = 0; k < (e < 3 ? 4 : 2); k++) wgmma_rl_112(ac, hh[4 * k], hh[4 * k + 1], hh[4 * k + 2], hh[4 * k + 3], bd + (k >> 1) * 512 + (k & 1) * 16, (e | k) != 0);
                WG_COMMIT();
                if (e > 0) { WG_WAIT(1); warp_arrive(BAR(B_EMPTY + e - 1)); }
            }
            PROFC(22);
            uint32_t ad = mkdesc(sb + 4 * 16384 + 8192 + w * 1024, DAN), bd = bx + 4 * 1024, fb_ = BAR(B_FULL + 4), eb_ = BAR(B_EMPTY + 3), par = sc;
#pragma unroll 1
            for (int e = 4; e < 25; e++) {
                mbar_wait_c(fb_, par);
                WG_FENCE();
                wgmma_ss_112<DAN, DW>(ac, ad, bd, 1);
                wgmma_ss_112<DAN, DW>(ac, ad + 256, bd + 16, 1);
                WG_COMMIT();
                WG_WAIT(1);
                warp_arrive(eb_);
                eb_ = fb_ + 8 * (B_EMPTY - B_FULL);
                ad += 1024; bd += 1024; fb_ += 8;
                if (e == 11 || e == 23) { ad -= 12 * 1024; bd -= 12 * 1024; fb_ -= 96; par = (par ^ 1) | sc; }
            }
            mbar_wait_cluster(BAR(B_PEER), sc);
            WG_WAIT(0);
            reg_fence<56>(ac);
            PROFC(24);
            uint32_t rdst, rbar;
            asm volatile("mapa.shared::cluster.u32 %0, %1, %2;" : "=r"(rdst) : "r"(sb + OFF_Y + (5 + w) * 16384 + t * 16), "r"(kh ^ 1 ^ sc));
            asm volatile("mapa.shared::cluster.u32 %0, %1, %2;" : "=r"(rbar) : "r"(BAR(B_XCH + w)), "r"(kh ^ 1 ^ sc));
#pragma unroll
            for (int g = 0; g < 7; g++) {
                const float v0 = ac[28 + 4 * g + 0], v1 = ac[28 + 4 * g + 1];
                const float v2 = ac[28 + 4 * g + 2], v3 = ac[28 + 4 * g + 3];
                if (!sc) asm volatile("st.async.shared::cluster.mbarrier::complete_tx::bytes.v4.f32 [%0], {%1,%2,%3,%4}, [%5];"
                             ::"r"(rdst + g * 2048), "f"(v0), "f"(v1), "f"(v2), "f"(v3), "r"(rbar) : "memory");
            }
            mbar_wait_cluster(BAR(B_XCH + w), sc);
            PROFC(25);
            uint32_t op[16];
#pragma unroll
            for (int g = 0; g < 7; g++) {
                const uint4 rv = *(const uint4*)(smem + OFF_Y + (5 + w) * 16384 + t * 16 + g * 2048);
                const float2 gb = *(const float2*)(smem + M_G + 224 + (8 * g + 2 * q) * 4);
                const float v0 = ac[4 * g + 0] + __uint_as_float(rv.x), v1 = ac[4 * g + 1] + __uint_as_float(rv.y);
                const float v2 = ac[4 * g + 2] + __uint_as_float(rv.z), v3 = ac[4 * g + 3] + __uint_as_float(rv.w);
                op[2 * g] = pack2(fmaf(gb.x, v0, bf_lo(x1p[2 * g])), fmaf(gb.y, v1, bf_hi(x1p[2 * g])));
                op[2 * g + 1] = pack2(fmaf(gb.x, v2, bf_lo(x1p[2 * g + 1])), fmaf(gb.y, v3, bf_hi(x1p[2 * g + 1])));
            }
            WAIT(B_EMPTY + 1, 0);
            const uint32_t oc = sb + OUT_STAGE + warp * 1792;
            const uint32_t oa = oc + (((lane >> 3) & 1) * 8 + (lane & 7)) * 112 + (lane >> 4) * 16;
            stsm4(oa, op[0], op[1], op[2], op[3]); stsm4(oa + 32, op[4], op[5], op[6], op[7]); stsm4(oa + 64, op[8], op[9], op[10], op[11]);
            asm volatile("stmatrix.sync.aligned.m8n8.x2.shared.b16 [%0], {%1,%2};" ::"r"(oa + 96), "r"(op[12]), "r"(op[13]));
            fence_async_smem();
            __syncwarp();
            asm volatile("{\n.reg .pred p;\nelect.sync _|p, 0xffffffff;\n@p cp.async.bulk.tensor.3d.global.shared::cta.bulk_group [%0, {%2, %3, %4}], [%1];\n"
                         "cp.async.bulk.commit_group;\ncp.async.bulk.wait_group.read 0;\n}" ::"l"(&p.om), "r"(oc), "r"(56 * j), "r"(128 * r + 16 * warp), "r"(0) : "memory");
        }
        PROFC(26);
        bar_sync(1 + w, 128);
        if (wi == 0) warp_arrive(BAR(B_DONE));
        return;
    }
    helper_late(p, r, j, warp PROF_ARGS);
}

#undef act
typedef CUresult (*EncodeFn)(CUtensorMap*, CUtensorMapDataType, cuuint32_t, void*, const cuuint64_t*, const cuuint64_t*, const cuuint32_t*,
                             const cuuint32_t*, CUtensorMapInterleave, CUtensorMapSwizzle, CUtensorMapL2promotion, CUtensorMapFloatOOBfill);

static void make_map(EncodeFn fn, CUtensorMap* m, const void* ptr, uint64_t d0, uint64_t d1, uint64_t d2, uint64_t s1, uint64_t s2,
                     uint32_t b0, uint32_t b1, uint32_t b2, CUtensorMapSwizzle sw) {
    cuuint64_t dims[3] = {d0, d1, d2}, strides[2] = {s1, s2};
    cuuint32_t box[3] = {b0, b1, b2}, es[3] = {1, 1, 1};
    CUresult rc = fn(m, CU_TENSOR_MAP_DATA_TYPE_BFLOAT16, 3, (void*)ptr, dims, strides, box, es, CU_TENSOR_MAP_INTERLEAVE_NONE, sw,
                     CU_TENSOR_MAP_L2_PROMOTION_L2_128B, CU_TENSOR_MAP_FLOAT_OOB_FILL_NONE);
    (void)rc;
}

extern "C" void kernel_launch(void* const* d_in, const int* in_sizes, int n_in, void* d_out, int out_size) {
    (void)in_sizes; (void)n_in; (void)out_size;
    static EncodeFn fn = nullptr;
    static uint32_t* act_base = nullptr;
    if (!fn) {
        cudaDriverEntryPointQueryResult st;
        cudaGetDriverEntryPoint("cuTensorMapEncodeTiled", (void**)&fn, cudaEnableDefault, &st);
        void* a = nullptr;
        cudaGetSymbolAddress(&a, g_act);
        act_base = (uint32_t*)(((uintptr_t)a + 0xFFFFF) & ~(uintptr_t)0xFFFFF);
        cudaFuncSetAttribute(fused_block_kernel, cudaFuncAttributeMaxDynamicSharedMemorySize, SMEM_BYTES);
    }
    Params p;
    p.x = (const bf16*)d_in[0];
    const bf16* wqkv = (const bf16*)d_in[1];
    p.wqkv = wqkv;
    p.wop = (const bf16*)d_in[2];
    p.wg = (const bf16*)d_in[4];
    p.wu = (const bf16*)d_in[5];
    p.wd = (const bf16*)d_in[6];
    p.c = (const bf16*)d_in[7];
    p.wmod = (const bf16*)d_in[8];
    p.out = (bf16*)d_out;
    p.zero = 0;
    p.actb = act_base;
    make_map(fn, &p.wm, p.wmod, 2688, 448, 1, 5376, 5376 * 448, 16, 224, 1, CU_TENSOR_MAP_SWIZZLE_NONE);
    make_map(fn, &p.wm2, p.wmod, 2688, 448, 1, 5376, 5376 * 448, 32, 224, 1, CU_TENSOR_MAP_SWIZZLE_NONE);
    make_map(fn, &p.om, p.out, 448, 2048, 1, 896, 896 * 2048, 56, 16, 1, CU_TENSOR_MAP_SWIZZLE_NONE);
    make_map(fn, &p.xm, p.x, 448, 2048, 1, 896, 896 * 2048, 64, 128, 1, CU_TENSOR_MAP_SWIZZLE_128B);
    make_map(fn, &p.qkv, wqkv, 1344, 448, 1, 2688, 2688 * 448, 64, 224, 1, CU_TENSOR_MAP_SWIZZLE_128B);
    make_map(fn, &p.wo, p.wop, 448, 448, 1, 896, 896 * 448, 64, 224, 1, CU_TENSOR_MAP_SWIZZLE_128B);
    make_map(fn, &p.ga, p.wg, 64, 448, 28, 3584, 128, 64, 32, 2, CU_TENSOR_MAP_SWIZZLE_128B);
    make_map(fn, &p.ua, p.wu, 64, 448, 28, 3584, 128, 64, 32, 2, CU_TENSOR_MAP_SWIZZLE_128B);
    make_map(fn, &p.gb, p.wg, 64, 448, 28, 3584, 128, 64, 64, 1, CU_TENSOR_MAP_SWIZZLE_128B);
    make_map(fn, &p.ub, p.wu, 64, 448, 28, 3584, 128, 64, 64, 1, CU_TENSOR_MAP_SWIZZLE_128B);
    make_map(fn, &p.gc, p.wg, 32, 448, 56, 3584, 64, 32, 64, 1, CU_TENSOR_MAP_SWIZZLE_64B);
    make_map(fn, &p.uc, p.wu, 32, 448, 56, 3584, 64, 32, 64, 1, CU_TENSOR_MAP_SWIZZLE_64B);
    make_map(fn, &p.dn, p.wd, 8, 1792, 56, 896, 16, 8, 32, 7, CU_TENSOR_MAP_SWIZZLE_NONE);
    fused_block_kernel<<<GRID, 384, SMEM_BYTES>>>(p);
}
```

```cpp
#include <cuda_runtime.h>
#include <cuda_bf16.h>
#include <cuda.h>
#include <stdint.h>

typedef __nv_bfloat16 bf16;

template<uint64_t CA, uint64_t CB> __device__ __forceinline__ void wgmma_sk_160(float* d, uint32_t da, uint32_t db, int sd) {
  asm volatile("{\n.reg .pred p;\n.reg .b64 a, b;\nsetp.ne.b32 p, %82, 0;\nmov.b64 a, {%80, %83};\nmov.b64 b, {%81, %84};\n"
    "wgmma.mma_async.sync.aligned.m64n160k16.f32.bf16.bf16 {%0,%1,%2,%3,%4,%5,%6,%7,%8,%9,%10,%11,%12,%13,%14,%15,%16,%17,%18,%19,%20,%21,%22,%23,%24,%25,%26,%27,%28,%29,%30,%31,%32,%33,%34,%35,%36,%37,%38,%39,%40,%41,%42,%43,%44,%45,%46,%47,%48,%49,%50,%51,%52,%53,%54,%55,%56,%57,%58,%59,%60,%61,%62,%63,%64,%65,%66,%67,%68,%69,%70,%71,%72,%73,%74,%75,%76,%77,%78,%79}, a, b, p, 1, 1, 0, 0;\n}\n"
    : "+f"(d[0]),"+f"(d[1]),"+f"(d[2]),"+f"(d[3]),"+f"(d[4]),"+f"(d[5]),"+f"(d[6]),"+f"(d[7]),"+f"(d[8]),"+f"(d[9]),"+f"(d[10]),"+f"(d[11]),"+f"(d[12]),"+f"(d[13]),"+f"(d[14]),"+f"(d[15]),"+f"(d[16]),"+f"(d[17]),"+f"(d[18]),"+f"(d[19]),"+f"(d[20]),"+f"(d[21]),"+f"(d[22]),"+f"(d[23]),"+f"(d[24]),"+f"(d[25]),"+f"(d[26]),"+f"(d[27]),"+f"(d[28]),"+f"(d[29]),"+f"(d[30]),"+f"(d[31]),"+f"(d[32]),"+f"(d[33]),"+f"(d[34]),"+f"(d[35]),"+f"(d[36]),"+f"(d[37]),"+f"(d[38]),"+f"(d[39]),"+f"(d[40]),"+f"(d[41]),"+f"(d[42]),"+f"(d[43]),"+f"(d[44]),"+f"(d[45]),"+f"(d[46]),"+f"(d[47]),"+f"(d[48]),"+f"(d[49]),"+f"(d[50]),"+f"(d[51]),"+f"(d[52]),"+f"(d[53]),"+f"(d[54]),"+f"(d[55]),"+f"(d[56]),"+f"(d[57]),"+f"(d[58]),"+f"(d[59]),"+f"(d[60]),"+f"(d[61]),"+f"(d[62]),"+f"(d[63]),"+f"(d[64]),"+f"(d[65]),"+f"(d[66]),"+f"(d[67]),"+f"(d[68]),"+f"(d[69]),"+f"(d[70]),"+f"(d[71]),"+f"(d[72]),"+f"(d[73]),"+f"(d[74]),"+f"(d[75]),"+f"(d[76]),"+f"(d[77]),"+f"(d[78]),"+f"(d[79])
    : "r"(da), "r"(db), "r"(sd), "n"((uint32_t)(CA >> 32)), "n"((uint32_t)(CB >> 32)));
}
__device__ __forceinline__ void wgmma_rl_56(float* d, uint32_t a0, uint32_t a1, uint32_t a2, uint32_t a3, uint64_t db, int sd) {
  asm volatile("{\n.reg .pred p;\nsetp.ne.b32 p, %33, 0;\n"
    "wgmma.mma_async.sync.aligned.m64n56k16.f32.bf16.bf16 {%0,%1,%2,%3,%4,%5,%6,%7,%8,%9,%10,%11,%12,%13,%14,%15,%16,%17,%18,%19,%20,%21,%22,%23,%24,%25,%26,%27}, {%28,%29,%30,%31}, %32, p, 1, 1, 1;\n}\n"
    : "+f"(d[0]),"+f"(d[1]),"+f"(d[2]),"+f"(d[3]),"+f"(d[4]),"+f"(d[5]),"+f"(d[6]),"+f"(d[7]),"+f"(d[8]),"+f"(d[9]),"+f"(d[10]),"+f"(d[11]),"+f"(d[12]),"+f"(d[13]),"+f"(d[14]),"+f"(d[15]),"+f"(d[16]),"+f"(d[17]),"+f"(d[18]),"+f"(d[19]),"+f"(d[20]),"+f"(d[21]),"+f"(d[22]),"+f"(d[23]),"+f"(d[24]),"+f"(d[25]),"+f"(d[26]),"+f"(d[27])
    : "r"(a0), "r"(a1), "r"(a2), "r"(a3), "l"(db), "r"(sd));
}
template<uint64_t CA, uint64_t CB> __device__ __forceinline__ void wgmma_ss_56(float* d, uint32_t da, uint32_t db, int sd) {
  asm volatile("{\n.reg .pred p;\n.reg .b64 a, b;\nsetp.ne.b32 p, %30, 0;\nmov.b64 a, {%28, %31};\nmov.b64 b, {%29, %32};\n"
    "wgmma.mma_async.sync.aligned.m64n56k16.f32.bf16.bf16 {%0,%1,%2,%3,%4,%5,%6,%7,%8,%9,%10,%11,%12,%13,%14,%15,%16,%17,%18,%19,%20,%21,%22,%23,%24,%25,%26,%27}, a, b, p, 1, 1, 0, 1;\n}\n"
    : "+f"(d[0]),"+f"(d[1]),"+f"(d[2]),"+f"(d[3]),"+f"(d[4]),"+f"(d[5]),"+f"(d[6]),"+f"(d[7]),"+f"(d[8]),"+f"(d[9]),"+f"(d[10]),"+f"(d[11]),"+f"(d[12]),"+f"(d[13]),"+f"(d[14]),"+f"(d[15]),"+f"(d[16]),"+f"(d[17]),"+f"(d[18]),"+f"(d[19]),"+f"(d[20]),"+f"(d[21]),"+f"(d[22]),"+f"(d[23]),"+f"(d[24]),"+f"(d[25]),"+f"(d[26]),"+f"(d[27])
    : "r"(da), "r"(db), "r"(sd), "n"((uint32_t)(CA >> 32)), "n"((uint32_t)(CB >> 32)));
}
__device__ __forceinline__ void wgmma_rl_256(float* d, uint32_t a0, uint32_t a1, uint32_t a2, uint32_t a3, uint64_t db, int sd) {
  asm volatile("{\n.reg .pred p;\nsetp.ne.b32 p, %133, 0;\n"
    "wgmma.mma_async.sync.aligned.m64n256k16.f32.bf16.bf16 {%0,%1,%2,%3,%4,%5,%6,%7,%8,%9,%10,%11,%12,%13,%14,%15,%16,%17,%18,%19,%20,%21,%22,%23,%24,%25,%26,%27,%28,%29,%30,%31,%32,%33,%34,%35,%36,%37,%38,%39,%40,%41,%42,%43,%44,%45,%46,%47,%48,%49,%50,%51,%52,%53,%54,%55,%56,%57,%58,%59,%60,%61,%62,%63,%64,%65,%66,%67,%68,%69,%70,%71,%72,%73,%74,%75,%76,%77,%78,%79,%80,%81,%82,%83,%84,%85,%86,%87,%88,%89,%90,%91,%92,%93,%94,%95,%96,%97,%98,%99,%100,%101,%102,%103,%104,%105,%106,%107,%108,%109,%110,%111,%112,%113,%114,%115,%116,%117,%118,%119,%120,%121,%122,%123,%124,%125,%126,%127}, {%128,%129,%130,%131}, %132, p, 1, 1, 1;\n}\n"
    : "+f"(d[0]),"+f"(d[1]),"+f"(d[2]),"+f"(d[3]),"+f"(d[4]),"+f"(d[5]),"+f"(d[6]),"+f"(d[7]),"+f"(d[8]),"+f"(d[9]),"+f"(d[10]),"+f"(d[11]),"+f"(d[12]),"+f"(d[13]),"+f"(d[14]),"+f"(d[15]),"+f"(d[16]),"+f"(d[17]),"+f"(d[18]),"+f"(d[19]),"+f"(d[20]),"+f"(d[21]),"+f"(d[22]),"+f"(d[23]),"+f"(d[24]),"+f"(d[25]),"+f"(d[26]),"+f"(d[27]),"+f"(d[28]),"+f"(d[29]),"+f"(d[30]),"+f"(d[31]),"+f"(d[32]),"+f"(d[33]),"+f"(d[34]),"+f"(d[35]),"+f"(d[36]),"+f"(d[37]),"+f"(d[38]),"+f"(d[39]),"+f"(d[40]),"+f"(d[41]),"+f"(d[42]),"+f"(d[43]),"+f"(d[44]),"+f"(d[45]),"+f"(d[46]),"+f"(d[47]),"+f"(d[48]),"+f"(d[49]),"+f"(d[50]),"+f"(d[51]),"+f"(d[52]),"+f"(d[53]),"+f"(d[54]),"+f"(d[55]),"+f"(d[56]),"+f"(d[57]),"+f"(d[58]),"+f"(d[59]),"+f"(d[60]),"+f"(d[61]),"+f"(d[62]),"+f"(d[63]),"+f"(d[64]),"+f"(d[65]),"+f"(d[66]),"+f"(d[67]),"+f"(d[68]),"+f"(d[69]),"+f"(d[70]),"+f"(d[71]),"+f"(d[72]),"+f"(d[73]),"+f"(d[74]),"+f"(d[75]),"+f"(d[76]),"+f"(d[77]),"+f"(d[78]),"+f"(d[79]),"+f"(d[80]),"+f"(d[81]),"+f"(d[82]),"+f"(d[83]),"+f"(d[84]),"+f"(d[85]),"+f"(d[86]),"+f"(d[87]),"+f"(d[88]),"+f"(d[89]),"+f"(d[90]),"+f"(d[91]),"+f"(d[92]),"+f"(d[93]),"+f"(d[94]),"+f"(d[95]),"+f"(d[96]),"+f"(d[97]),"+f"(d[98]),"+f"(d[99]),"+f"(d[100]),"+f"(d[101]),"+f"(d[102]),"+f"(d[103]),"+f"(d[104]),"+f"(d[105]),"+f"(d[106]),"+f"(d[107]),"+f"(d[108]),"+f"(d[109]),"+f"(d[110]),"+f"(d[111]),"+f"(d[112]),"+f"(d[113]),"+f"(d[114]),"+f"(d[115]),"+f"(d[116]),"+f"(d[117]),"+f"(d[118]),"+f"(d[119]),"+f"(d[120]),"+f"(d[121]),"+f"(d[122]),"+f"(d[123]),"+f"(d[124]),"+f"(d[125]),"+f"(d[126]),"+f"(d[127])
    : "r"(a0), "r"(a1), "r"(a2), "r"(a3), "l"(db), "r"(sd));
}
template<uint64_t CA, uint64_t CB> __device__ __forceinline__ void wgmma_ss_128(float* d, uint32_t da, uint32_t db, int sd) {
  asm volatile("{\n.reg .pred p;\n.reg .b64 a, b;\nsetp.ne.b32 p, %66, 0;\nmov.b64 a, {%64, %67};\nmov.b64 b, {%65, %68};\n"
    "wgmma.mma_async.sync.aligned.m64n128k16.f32.bf16.bf16 {%0,%1,%2,%3,%4,%5,%6,%7,%8,%9,%10,%11,%12,%13,%14,%15,%16,%17,%18,%19,%20,%21,%22,%23,%24,%25,%26,%27,%28,%29,%30,%31,%32,%33,%34,%35,%36,%37,%38,%39,%40,%41,%42,%43,%44,%45,%46,%47,%48,%49,%50,%51,%52,%53,%54,%55,%56,%57,%58,%59,%60,%61,%62,%63}, a, b, p, 1, 1, 0, 1;\n}\n"
    : "+f"(d[0]),"+f"(d[1]),"+f"(d[2]),"+f"(d[3]),"+f"(d[4]),"+f"(d[5]),"+f"(d[6]),"+f"(d[7]),"+f"(d[8]),"+f"(d[9]),"+f"(d[10]),"+f"(d[11]),"+f"(d[12]),"+f"(d[13]),"+f"(d[14]),"+f"(d[15]),"+f"(d[16]),"+f"(d[17]),"+f"(d[18]),"+f"(d[19]),"+f"(d[20]),"+f"(d[21]),"+f"(d[22]),"+f"(d[23]),"+f"(d[24]),"+f"(d[25]),"+f"(d[26]),"+f"(d[27]),"+f"(d[28]),"+f"(d[29]),"+f"(d[30]),"+f"(d[31]),"+f"(d[32]),"+f"(d[33]),"+f"(d[34]),"+f"(d[35]),"+f"(d[36]),"+f"(d[37]),"+f"(d[38]),"+f"(d[39]),"+f"(d[40]),"+f"(d[41]),"+f"(d[42]),"+f"(d[43]),"+f"(d[44]),"+f"(d[45]),"+f"(d[46]),"+f"(d[47]),"+f"(d[48]),"+f"(d[49]),"+f"(d[50]),"+f"(d[51]),"+f"(d[52]),"+f"(d[53]),"+f"(d[54]),"+f"(d[55]),"+f"(d[56]),"+f"(d[57]),"+f"(d[58]),"+f"(d[59]),"+f"(d[60]),"+f"(d[61]),"+f"(d[62]),"+f"(d[63])
    : "r"(da), "r"(db), "r"(sd), "n"((uint32_t)(CA >> 32)), "n"((uint32_t)(CB >> 32)));
}
template<uint64_t CA, uint64_t CB> __device__ __forceinline__ void wgmma_ss_64(float* d, uint32_t da, uint32_t db, int sd) {
  asm volatile("{\n.reg .pred p;\n.reg .b64 a, b;\nsetp.ne.b32 p, %34, 0;\nmov.b64 a, {%32, %35};\nmov.b64 b, {%33, %36};\n"
    "wgmma.mma_async.sync.aligned.m64n64k16.f32.bf16.bf16 {%0,%1,%2,%3,%4,%5,%6,%7,%8,%9,%10,%11,%12,%13,%14,%15,%16,%17,%18,%19,%20,%21,%22,%23,%24,%25,%26,%27,%28,%29,%30,%31}, a, b, p, 1, 1, 0, 1;\n}\n"
    : "+f"(d[0]),"+f"(d[1]),"+f"(d[2]),"+f"(d[3]),"+f"(d[4]),"+f"(d[5]),"+f"(d[6]),"+f"(d[7]),"+f"(d[8]),"+f"(d[9]),"+f"(d[10]),"+f"(d[11]),"+f"(d[12]),"+f"(d[13]),"+f"(d[14]),"+f"(d[15]),"+f"(d[16]),"+f"(d[17]),"+f"(d[18]),"+f"(d[19]),"+f"(d[20]),"+f"(d[21]),"+f"(d[22]),"+f"(d[23]),"+f"(d[24]),"+f"(d[25]),"+f"(d[26]),"+f"(d[27]),"+f"(d[28]),"+f"(d[29]),"+f"(d[30]),"+f"(d[31])
    : "r"(da), "r"(db), "r"(sd), "n"((uint32_t)(CA >> 32)), "n"((uint32_t)(CB >> 32)));
}
template<uint64_t CA, uint64_t CB> __device__ __forceinline__ void wgmma_ss_112(float* d, uint32_t da, uint32_t db, int sd) {
  asm volatile("{\n.reg .pred p;\n.reg .b64 a, b;\nsetp.ne.b32 p, %58, 0;\nmov.b64 a, {%56, %59};\nmov.b64 b, {%57, %60};\n"
    "wgmma.mma_async.sync.aligned.m64n112k16.f32.bf16.bf16 {%0,%1,%2,%3,%4,%5,%6,%7,%8,%9,%10,%11,%12,%13,%14,%15,%16,%17,%18,%19,%20,%21,%22,%23,%24,%25,%26,%27,%28,%29,%30,%31,%32,%33,%34,%35,%36,%37,%38,%39,%40,%41,%42,%43,%44,%45,%46,%47,%48,%49,%50,%51,%52,%53,%54,%55}, a, b, p, 1, 1, 0, 1;\n}\n"
    : "+f"(d[0]),"+f"(d[1]),"+f"(d[2]),"+f"(d[3]),"+f"(d[4]),"+f"(d[5]),"+f"(d[6]),"+f"(d[7]),"+f"(d[8]),"+f"(d[9]),"+f"(d[10]),"+f"(d[11]),"+f"(d[12]),"+f"(d[13]),"+f"(d[14]),"+f"(d[15]),"+f"(d[16]),"+f"(d[17]),"+f"(d[18]),"+f"(d[19]),"+f"(d[20]),"+f"(d[21]),"+f"(d[22]),"+f"(d[23]),"+f"(d[24]),"+f"(d[25]),"+f"(d[26]),"+f"(d[27]),"+f"(d[28]),"+f"(d[29]),"+f"(d[30]),"+f"(d[31]),"+f"(d[32]),"+f"(d[33]),"+f"(d[34]),"+f"(d[35]),"+f"(d[36]),"+f"(d[37]),"+f"(d[38]),"+f"(d[39]),"+f"(d[40]),"+f"(d[41]),"+f"(d[42]),"+f"(d[43]),"+f"(d[44]),"+f"(d[45]),"+f"(d[46]),"+f"(d[47]),"+f"(d[48]),"+f"(d[49]),"+f"(d[50]),"+f"(d[51]),"+f"(d[52]),"+f"(d[53]),"+f"(d[54]),"+f"(d[55])
    : "r"(da), "r"(db), "r"(sd), "n"((uint32_t)(CA >> 32)), "n"((uint32_t)(CB >> 32)));
}
__device__ __forceinline__ void wgmma_rl_112(float* d, uint32_t a0, uint32_t a1, uint32_t a2, uint32_t a3, uint64_t db, int sd) {
  asm volatile("{\n.reg .pred p;\nsetp.ne.b32 p, %61, 0;\n"
    "wgmma.mma_async.sync.aligned.m64n112k16.f32.bf16.bf16 {%0,%1,%2,%3,%4,%5,%6,%7,%8,%9,%10,%11,%12,%13,%14,%15,%16,%17,%18,%19,%20,%21,%22,%23,%24,%25,%26,%27,%28,%29,%30,%31,%32,%33,%34,%35,%36,%37,%38,%39,%40,%41,%42,%43,%44,%45,%46,%47,%48,%49,%50,%51,%52,%53,%54,%55}, {%56,%57,%58,%59}, %60, p, 1, 1, 1;\n}\n"
    : "+f"(d[0]),"+f"(d[1]),"+f"(d[2]),"+f"(d[3]),"+f"(d[4]),"+f"(d[5]),"+f"(d[6]),"+f"(d[7]),"+f"(d[8]),"+f"(d[9]),"+f"(d[10]),"+f"(d[11]),"+f"(d[12]),"+f"(d[13]),"+f"(d[14]),"+f"(d[15]),"+f"(d[16]),"+f"(d[17]),"+f"(d[18]),"+f"(d[19]),"+f"(d[20]),"+f"(d[21]),"+f"(d[22]),"+f"(d[23]),"+f"(d[24]),"+f"(d[25]),"+f"(d[26]),"+f"(d[27]),"+f"(d[28]),"+f"(d[29]),"+f"(d[30]),"+f"(d[31]),"+f"(d[32]),"+f"(d[33]),"+f"(d[34]),"+f"(d[35]),"+f"(d[36]),"+f"(d[37]),"+f"(d[38]),"+f"(d[39]),"+f"(d[40]),"+f"(d[41]),"+f"(d[42]),"+f"(d[43]),"+f"(d[44]),"+f"(d[45]),"+f"(d[46]),"+f"(d[47]),"+f"(d[48]),"+f"(d[49]),"+f"(d[50]),"+f"(d[51]),"+f"(d[52]),"+f"(d[53]),"+f"(d[54]),"+f"(d[55])
    : "r"(a0), "r"(a1), "r"(a2), "r"(a3), "l"(db), "r"(sd));
}

constexpr int DM = 448;
constexpr int NCTA = 128;
#define MAPPING 1
#define GRID 128
#define PINGPONG 0
#define WIN 6
#define WIN_END 25
#define UNR_B 1
#define UNR_C 1
constexpr int kB = UNR_B, kC = UNR_C;
#define LIKELY(x) __builtin_expect(!!(x), 1)
#define PACE 1
#define PACE_END 6
#define GEMV_AT 1
#define NPRE 14
#define ATT_OFF 0
#define ATT_WG 1
#define XFIRST 7
#define KDELAY 0
#define KEARLY 1
#define VPRE 3
#define VGATE 0
#define MAP_S 4
constexpr int SPIN_LIMIT = 1 << 22;

constexpr uint32_t OFF_X = 0, OFF_Y = 114688, OFF_MISC = 229376, SMEM_BYTES = 232448;
constexpr uint32_t Y_VR = 0, Y_K = 28672, Y_KOWN = 57344, Y_VOWN = 71680, Y_Q = 86016;
constexpr uint32_t HALF = 57344;
constexpr uint32_t X_STAT = 49152;
constexpr uint32_t OUT_STAGE = 16384;
constexpr uint32_t M_BAR = OFF_MISC;
constexpr uint32_t M_ST = OFF_MISC + 512;
constexpr uint32_t M_G = OFF_MISC + 2304;
constexpr uint32_t M_EPOCH = OFF_MISC + 3040;
enum { B_XFULL = 0, B_FULLK = 7, B_FULLV = 8, B_FULLQ, B_KRFULL, B_VRFULL, B_WOFULL, B_XCH, B_MOD1 = 15, B_FULL = 16, B_WMFULL = 30,
       B_EMPTY = 32, B_XFREE = B_EMPTY + 12, B_GEMV, B_PEER,
       B_PUB = 47,
       B_WMFREE = 56, B_HRDY, B_GFULL = B_HRDY + 3, B_DONE = 31, B_DUMMY = B_GEMV };

__device__ uint32_t g_ticket;
__device__ __align__(128) uint32_t g_mod[8 * 6 * DM];
__device__ __align__(128) uint32_t g_flag[144 * 128];
constexpr int RB_WORDS = 262144, RB_KV = 0, RB_O = 57344, RB_X1 = 86016, RB_H2 = 143360, RB_ST = 258048;
__device__ __align__(128) uint32_t g_act[18 * RB_WORDS];
__device__ __align__(128) uint32_t g_wd[56 * 4 * 1792];
#define PROFH(id)
#define PROFH1(id)
#define PROFC(id)

struct alignas(64) Params {
    CUtensorMap wm, wm2, om, xm, qkv, wo, ga, ua, gb, ub, gc, uc, dn;
    const bf16 *x, *c, *wqkv, *wmod, *wg, *wu, *wd, *wop;
    bf16* out;
    uint32_t* actb;
    uint32_t zero;
};

__device__ __forceinline__ void mbar_init(uint32_t bar, int cnt) { asm volatile("mbarrier.init.shared::cta.b64 [%0], %1;" ::"r"(bar), "r"(cnt) : "memory"); }
__device__ __forceinline__ void mbar_expect_tx(uint32_t bar, uint32_t bytes) { asm volatile("mbarrier.arrive.expect_tx.shared::cta.b64 _, [%0], %1;" ::"r"(bar), "r"(bytes) : "memory"); }
__device__ __forceinline__ void mbar_arrive(uint32_t bar) { asm volatile("mbarrier.arrive.shared::cta.b64 _, [%0];" ::"r"(bar) : "memory"); }
__device__ __forceinline__ void mbar_wait(uint32_t bar, uint32_t parity) {
    uint32_t ok; int n = 0;
    do {
        asm volatile("{\n.reg .pred p;\nmbarrier.try_wait.parity.shared::cta.b64 p, [%1], %2;\nselp.u32 %0, 1, 0, p;\n}" : "=r"(ok) : "r"(bar), "r"(parity) : "memory");
        if (++n > SPIN_LIMIT) __trap();
    } while (!ok);
}
__device__ __forceinline__ void mbar_wait_c(uint32_t bar, uint32_t parity) {
    asm volatile("{\n.reg .pred p;\nWL:\nmbarrier.try_wait.parity.shared::cta.b64 p, [%0], %1, 0x989680;\n@!p bra WL;\n}" ::"r"(bar), "r"(parity) : "memory");
}
__device__ __forceinline__ void mbar_wait_cluster(uint32_t bar, uint32_t parity) {
    asm volatile("{\n.reg .pred p;\nWL:\nmbarrier.try_wait.parity.acquire.cluster.shared::cta.b64 p, [%0], %1, 0x989680;\n@!p bra WL;\n}" ::"r"(bar), "r"(parity) : "memory");
}
__device__ __forceinline__ void warp_arrive(uint32_t bar) {
    __syncwarp();
    asm volatile("{\n.reg .pred p;\nelect.sync _|p, 0xffffffff;\n@p mbarrier.arrive.shared::cta.b64 _, [%0];\n}" ::"r"(bar) : "memory");
}
__device__ __forceinline__ int opaque(int v) { return __shfl_sync(~0u, v, 0); }
__device__ __forceinline__ int fresh_tid() { int v; asm volatile("mov.u32 %0, %%tid.x;" : "=r"(v)); return v; }
__device__ __forceinline__ void bar_sync(int id, int n) { asm volatile("bar.sync %0, %1;" ::"r"(id), "r"(n) : "memory"); }
__device__ __forceinline__ void bar_arrive(int id, int n) { asm volatile("bar.arrive %0, %1;" ::"r"(id), "r"(n) : "memory"); }
__device__ __forceinline__ void fence_async_smem() { asm volatile("fence.proxy.async.shared::cta;" ::: "memory"); }
__device__ __forceinline__ void fence_async_global() { asm volatile("fence.proxy.async.global;" ::: "memory"); }
__device__ __forceinline__ void fence_gpu() { asm volatile("fence.release.gpu;" ::: "memory"); }
__device__ __forceinline__ void tma3(uint32_t dst, const CUtensorMap* m, int c0, int c1, int c2, uint32_t bar) {
    asm volatile("cp.async.bulk.tensor.3d.shared::cluster.global.mbarrier::complete_tx::bytes [%0], [%1, {%3, %4, %5}], [%2];"
                 ::"r"(dst), "l"(m), "r"(bar), "r"(c0), "r"(c1), "r"(c2) : "memory");
}
__device__ __forceinline__ void bulk_load(uint32_t dst, const void* src, uint32_t bytes, uint32_t bar) {
    asm volatile("cp.async.bulk.shared::cluster.global.mbarrier::complete_tx::bytes [%0], [%1], %2, [%3];" ::"r"(dst), "l"(src), "r"(bytes), "r"(bar) : "memory");
}
__device__ __forceinline__ void expect_e(uint32_t bar, uint32_t bytes) {
    asm volatile("{\n.reg .pred p;\nelect.sync _|p, 0xffffffff;\n@p mbarrier.arrive.expect_tx.shared::cta.b64 _, [%0], %1;\n}" ::"r"(bar), "r"(bytes) : "memory");
}
__device__ __forceinline__ void tma3_e(uint32_t dst, const CUtensorMap* m, int c0, int c1, int c2, uint32_t bar) {
    asm volatile("{\n.reg .pred p;\nelect.sync _|p, 0xffffffff;\n@p cp.async.bulk.tensor.3d.shared::cluster.global.mbarrier::complete_tx::bytes [%0], [%1, {%3, %4, %5}], [%2];\n}"
                 ::"r"(dst), "l"(m), "r"(bar), "r"(c0), "r"(c1), "r"(c2) : "memory");
}
__device__ __forceinline__ void bulk_e(uint32_t dst, const void* src, uint32_t bytes, uint32_t bar) {
    asm volatile("{\n.reg .pred p;\nelect.sync _|p, 0xffffffff;\n@p cp.async.bulk.shared::cluster.global.mbarrier::complete_tx::bytes [%0], [%1], %2, [%3];\n}"
                 ::"r"(dst), "l"(src), "r"(bytes), "r"(bar) : "memory");
}
__device__ __forceinline__ void init_e(uint32_t bar, int cnt) {
    asm volatile("{\n.reg .pred p;\nelect.sync _|p, 0xffffffff;\n@p mbarrier.init.shared::cta.b64 [%0], %1;\n}" ::"r"(bar), "r"(cnt) : "memory");
}
__device__ __forceinline__ void l2_prefetch_e(const void* src, uint32_t bytes) {
    asm volatile("{\n.reg .pred p;\nelect.sync _|p, 0xffffffff;\n@p cp.async.bulk.prefetch.L2.global [%0], %1;\n}" ::"l"(src), "r"(bytes) : "memory");
}
__device__ __forceinline__ uint32_t ld_relaxed(const uint32_t* p) { uint32_t v; asm volatile("ld.relaxed.gpu.global.u32 %0, [%1];" : "=r"(v) : "l"(p) : "memory"); return v; }
__device__ __forceinline__ void st_relaxed(uint32_t* p, uint32_t v) { asm volatile("st.relaxed.gpu.global.u32 [%0], %1;" ::"l"(p), "r"(v) : "memory"); }
__device__ __forceinline__ uint4 ld_relaxed4(const uint4* p) { uint4 v; asm volatile("ld.relaxed.gpu.global.v4.u32 {%0,%1,%2,%3}, [%4];" : "=r"(v.x), "=r"(v.y), "=r"(v.z), "=r"(v.w) : "l"(p) : "memory"); return v; }
__device__ __forceinline__ void st_relaxed4(uint4* p, uint4 v) { asm volatile("st.relaxed.gpu.global.v4.u32 [%0], {%1,%2,%3,%4};" ::"l"(p), "r"(v.x), "r"(v.y), "r"(v.z), "r"(v.w) : "memory"); }
__device__ __forceinline__ uint4 ldg_nc4(const void* p) { uint4 v; asm volatile("ld.global.nc.L1::no_allocate.v4.u32 {%0,%1,%2,%3}, [%4];" : "=r"(v.x), "=r"(v.y), "=r"(v.z), "=r"(v.w) : "l"(p)); return v; }
__device__ __forceinline__ uint32_t ldg_nc(const void* p) { uint32_t v; asm volatile("ld.global.nc.u32 %0, [%1];" : "=r"(v) : "l"(p)); return v; }
__device__ __forceinline__ uint32_t ld_acquire(const uint32_t* p) { uint32_t v; asm volatile("ld.acquire.gpu.global.u32 %0, [%1];" : "=r"(v) : "l"(p) : "memory"); return v; }
__device__ __forceinline__ uint4 lds4(uint32_t a) { uint4 v; asm volatile("ld.shared.v4.u32 {%0,%1,%2,%3}, [%4];" : "=r"(v.x), "=r"(v.y), "=r"(v.z), "=r"(v.w) : "r"(a) : "memory"); return v; }
__device__ __forceinline__ float2 lds2f(uint32_t a) { float2 v; asm volatile("ld.shared.v2.f32 {%0,%1}, [%2];" : "=f"(v.x), "=f"(v.y) : "r"(a) : "memory"); return v; }
__device__ __forceinline__ uint32_t lds1(uint32_t a) { uint32_t v; asm volatile("ld.shared.u32 %0, [%1];" : "=r"(v) : "r"(a) : "memory"); return v; }
__device__ __forceinline__ void sts4(uint32_t a, uint4 v) { asm volatile("st.shared.v4.u32 [%0], {%1,%2,%3,%4};" ::"r"(a), "r"(v.x), "r"(v.y), "r"(v.z), "r"(v.w) : "memory"); }
__device__ __forceinline__ void sts2(uint32_t a, uint32_t x, uint32_t y) { asm volatile("st.shared.v2.u32 [%0], {%1,%2};" ::"r"(a), "r"(x), "r"(y) : "memory"); }
__device__ __forceinline__ void sts1(uint32_t a, uint32_t v) { asm volatile("st.shared.u32 [%0], %1;" ::"r"(a), "r"(v) : "memory"); }
__device__ __forceinline__ void stsm4(uint32_t a, uint32_t r0, uint32_t r1, uint32_t r2, uint32_t r3) {
    asm volatile("stmatrix.sync.aligned.m8n8.x4.shared.b16 [%0], {%1,%2,%3,%4};" ::"r"(a), "r"(r0), "r"(r1), "r"(r2), "r"(r3));
}
__device__ __forceinline__ uint32_t pack2(float lo, float hi) { uint32_t r; asm("cvt.rn.bf16x2.f32 %0, %1, %2;" : "=r"(r) : "f"(hi), "f"(lo)); return r; }
__device__ __forceinline__ uint32_t pack2_relu(float lo, float hi) { uint32_t r; asm("cvt.rn.relu.bf16x2.f32 %0, %1, %2;" : "=r"(r) : "f"(hi), "f"(lo)); return r; }
__device__ __forceinline__ uint32_t hfma2(uint32_t a, uint32_t b, uint32_t c) { uint32_t r; asm("fma.rn.bf16x2 %0, %1, %2, %3;" : "=r"(r) : "r"(a), "r"(b), "r"(c)); return r; }
__device__ __forceinline__ uint32_t hmul2(uint32_t a, uint32_t b) { uint32_t r; asm("mul.rn.bf16x2 %0, %1, %2;" : "=r"(r) : "r"(a), "r"(b)); return r; }
__device__ __forceinline__ float bf_lo(uint32_t v) { return __uint_as_float(v << 16); }
__device__ __forceinline__ float bf_hi(uint32_t v) { return __uint_as_float(v & 0xFFFF0000u); }
__device__ __forceinline__ float bf_round(float v) { return bf_lo(pack2(v, 0.f)); }
__device__ __forceinline__ float ex2(float x) { float r; asm("ex2.approx.ftz.f32 %0, %1;" : "=f"(r) : "f"(x)); return r; }
__device__ __forceinline__ void mma16816(float* d, uint32_t a0, uint32_t a1, uint32_t a2, uint32_t a3, uint32_t b0, uint32_t b1) {
    asm("mma.sync.aligned.m16n8k16.row.col.f32.bf16.bf16.f32 {%0,%1,%2,%3}, {%4,%5,%6,%7}, {%8,%9}, {%0,%1,%2,%3};"
        : "+f"(d[0]), "+f"(d[1]), "+f"(d[2]), "+f"(d[3]) : "r"(a0), "r"(a1), "r"(a2), "r"(a3), "r"(b0), "r"(b1));
}
__device__ __forceinline__ void mma16816_first(float* d, uint32_t a0, uint32_t a1, uint32_t a2, uint32_t a3, uint32_t b0, uint32_t b1) {
    asm volatile("mma.sync.aligned.m16n8k16.row.col.f32.bf16.bf16.f32 {%0,%1,%2,%3}, {%4,%5,%6,%7}, {%8,%9}, {%10,%10,%10,%10};"
        : "=f"(d[0]), "=f"(d[1]), "=f"(d[2]), "=f"(d[3]) : "r"(a0), "r"(a1), "r"(a2), "r"(a3), "r"(b0), "r"(b1), "f"(0.f));
}
__device__ __forceinline__ void mma16816_v(float* d, uint32_t a0, uint32_t a1, uint32_t a2, uint32_t a3, uint32_t b0, uint32_t b1) {
    asm volatile("mma.sync.aligned.m16n8k16.row.col.f32.bf16.bf16.f32 {%0,%1,%2,%3}, {%4,%5,%6,%7}, {%8,%9}, {%0,%1,%2,%3};"
        : "+f"(d[0]), "+f"(d[1]), "+f"(d[2]), "+f"(d[3]) : "r"(a0), "r"(a1), "r"(a2), "r"(a3), "r"(b0), "r"(b1));
}
__device__ __forceinline__ void mma1688(float* d, uint32_t a0, uint32_t a1, uint32_t b0) {
    asm("mma.sync.aligned.m16n8k8.row.col.f32.bf16.bf16.f32 {%0,%1,%2,%3}, {%4,%5}, {%6}, {%0,%1,%2,%3};"
        : "+f"(d[0]), "+f"(d[1]), "+f"(d[2]), "+f"(d[3]) : "r"(a0), "r"(a1), "r"(b0));
}
__device__ __forceinline__ void ldsm4(uint32_t a, uint32_t* r) {
    asm volatile("ldmatrix.sync.aligned.m8n8.x4.shared.b16 {%0,%1,%2,%3}, [%4];" : "=r"(r[0]), "=r"(r[1]), "=r"(r[2]), "=r"(r[3]) : "r"(a));
}
__device__ __forceinline__ void ldsm4t(uint32_t a, uint32_t* r) {
    asm volatile("ldmatrix.sync.aligned.m8n8.x4.trans.shared.b16 {%0,%1,%2,%3}, [%4];" : "=r"(r[0]), "=r"(r[1]), "=r"(r[2]), "=r"(r[3]) : "r"(a));
}
__device__ __forceinline__ uint32_t nz(uint32_t v) { uint32_t r; asm("max.u32 %0, %1, 1;" : "=r"(r) : "r"(v)); return r; }
__device__ __forceinline__ float rcp(float x) { float r; asm("rcp.approx.ftz.f32 %0, %1;" : "=f"(r) : "f"(x)); return r; }
__device__ __forceinline__ uint2 ld_relaxed2(const void* p) { uint2 v; asm volatile("ld.relaxed.gpu.global.v2.u32 {%0,%1}, [%2];" : "=r"(v.x), "=r"(v.y) : "l"(p) : "memory"); return v; }
__device__ __forceinline__ void st_relaxed2(void* p, uint32_t x, uint32_t y) { asm volatile("st.relaxed.gpu.global.v2.u32 [%0], {%1,%2};" ::"l"(p), "r"(max(x, 1u)), "r"(max(y, 1u)) : "memory"); }
__host__ __device__ constexpr uint64_t dconst(uint32_t lbo, uint32_t sbo, uint32_t swz) {
    return ((uint64_t)(lbo >> 4) << 16) | ((uint64_t)(sbo >> 4) << 32) | ((uint64_t)swz << 62);
}
__device__ __forceinline__ uint32_t mkdesc(uint32_t addr, uint64_t c) { return (uint32_t)c | ((addr & 0x3FFFF) >> 4); }
#define WG_FENCE() asm volatile("wgmma.fence.sync.aligned;" ::: "memory")
#define WG_COMMIT() asm volatile("wgmma.commit_group.sync.aligned;" ::: "memory")
#define WG_WAIT(n) asm volatile("wgmma.wait_group.sync.aligned %0;" ::"n"(n) : "memory")
template <int N> __device__ __forceinline__ void reg_fence(float* d) {
#pragma unroll
    for (int i = 0; i < N; i++) asm volatile("" : "+f"(d[i])::"memory");
}
template <int N> __device__ __forceinline__ void reg_def(float* d) {
#pragma unroll
    for (int i = 0; i < N; i++) asm volatile("" : "=f"(d[i]));
}
template <int N> __device__ __forceinline__ void reg_def(uint32_t* d) {
#pragma unroll
    for (int i = 0; i < N; i++) asm volatile("" : "=r"(d[i]));
}
__device__ __forceinline__ bool is_unset(uint4 v) { return min(min(v.x, v.y), min(v.z, v.w)) == 0u; }
__device__ __forceinline__ uint4 nz4(uint32_t a, uint32_t b, uint32_t c, uint32_t d) { return make_uint4(max(a, 1u), max(b, 1u), max(c, 1u), max(d, 1u)); }
__device__ __forceinline__ void wait_flags(const uint32_t* p, uint32_t target, uint32_t mask) {
    int n = 0;
    while (~__ballot_sync(~0u, (int)(ld_relaxed(p) - target) >= 0) & mask) { if (++n > SPIN_LIMIT) __trap(); }
    asm volatile("fence.acquire.gpu;" ::: "memory");
}
__device__ __forceinline__ float silu_bf(uint32_t cbits) {
    const float c = __uint_as_float(cbits << 16);
    return bf_round(__fdividef(c, 1.f + fminf(ex2(-1.4426950408889634f * c), 1e30f)));
}
__device__ __forceinline__ void gemv_part(uint32_t wmbuf, int wp, int lane) {
    const uint32_t wa = wmbuf + wp * 512 + (8 * (lane >> 4) + (lane & 7)) * 32 + ((lane >> 3) & 1) * 16;
    float d[4] = {};
#pragma unroll
    for (int i = 0; i < 4; i++) {
        uint32_t A[4];
        const float2 v = lds2f(wmbuf + 28672 + (wp + 8 * i) * 32 + (lane & 3) * 8);
        ldsm4t(wa + (i < 3 || wp < 4 ? i : 0) * 4096, A);
        mma16816(d, A[0], A[1], A[2], A[3], __float_as_uint(v.x), __float_as_uint(v.y));
    }
    if ((lane & 3) == 0) {
        sts1(wmbuf + 29696 + (wp * 16 + (lane >> 2)) * 4, __float_as_uint(d[0]));
        sts1(wmbuf + 29696 + (wp * 16 + 8 + (lane >> 2)) * 4, __float_as_uint(d[2]));
    }
}
__device__ __forceinline__ uint32_t mod_word(float v, int col, uint32_t target) {
    v = bf_round(v);
    if ((col >= DM && col < 2 * DM) || (col >= 4 * DM && col < 5 * DM)) v += 1.f;
    return (pack2(v, 0.f) << 16) | (target & 0xFFFFu);
}
__device__ __forceinline__ const uint4* mod_src(int i, int r, int j, bool p2) {
    i = min(i, p2 ? 251 : 223);
    return (const uint4*)g_mod + (r & 7) * (6 * DM / 4) + (i < 224 ? (p2 ? 336 : 0) + i : (i < 238 ? 14 * j + i : 14 * j + i + 322));
}
__device__ __forceinline__ void mod_store(uint32_t sb, uint4 v, const uint4* src, int i) {
    const uint32_t tag = lds1(sb + M_EPOCH) + 1;
    while (__any_sync(~0u, (((v.x ^ tag) | (v.y ^ tag) | (v.z ^ tag) | (v.w ^ tag)) & 0xFFFFu) != 0u)) v = ld_relaxed4(src);
    if (i < 224) {
        const int isc = i >= 112, c4 = i - 112 * isc;
        const uint32_t a = sb + M_ST + (c4 >> 2) * 64 + (c4 & 1) * 32 + (c4 & 2) * 4 + (isc ? 0 : 4);
        sts1(a, __byte_perm(v.x, v.y, 0x7632));
        sts1(a + 16, __byte_perm(v.z, v.w, 0x7632));
    } else if (i < 252) {
        sts4(sb + M_G + (i - 224) * 16, make_uint4(v.x & 0xFFFF0000u, v.y & 0xFFFF0000u, v.z & 0xFFFF0000u, v.w & 0xFFFF0000u));
    }
}
__device__ __forceinline__ int pass_f(int fs, int ps) { return 224 * fs + ((fs & 1) ? (ps == 0 ? 96 : ps == 1 ? 32 : 0) : (ps == 0 ? 0 : ps == 1 ? 128 : 192)); }
__device__ __forceinline__ constexpr uint32_t slot_off(int l) { return l * 16384; }
__device__ __forceinline__ constexpr int g1_slot(int s) { return s % 7; }
__device__ __noinline__ void x1_fix(const uint32_t* g, uint32_t sa, int s) {
#pragma unroll 1
    for (int k = 4 * s; k < 4 * s + 4;) {
        const uint4 v = ld_relaxed4((const uint4*)(g + k * 256));
        sts4(sa + k * 1024, v);
        k += 2 * __all_sync(~0u, min(min(v.x, v.y), min(v.z, v.w)) != 0u);
    }
    __syncwarp();
}
__device__ __forceinline__ void ln_coeffs(float mean, float msq, uint32_t& r2, uint32_t& n2) {
    const float rs = bf_round(rsqrtf(fmaxf(msq - mean * mean, 0.f) + 1e-5f));
    r2 = pack2(rs, rs);
    n2 = pack2(-mean * rs, -mean * rs);
}

#define LOADW bulk_e(dst, g_wd + (size_t)((f >> 5) * 4 + nq) * 1792, 7168, bar);
template <int sec> __device__ __forceinline__ void ring_loader(const Params& p, uint32_t sb_, int r_, int j_, int lane) {
    const uint32_t sb = opaque(sb_);
    const int r = opaque(r_), j = opaque(j_), nq = j >> 1, fs = 4 * (j & 1) + nq;
    const int fa = pass_f(fs, 0), fb = pass_f(fs, 1), fc = pass_f(fs, 2);
    const uint32_t* h2src = (const uint32_t*)__shfl_sync(~0u, (unsigned long long)(p.actb + (size_t)r * RB_WORDS + RB_H2), 0);
    const CUtensorMap* gmap = (const CUtensorMap*)__shfl_sync(~0u, (unsigned long long)(&p.ga + sec), 0);
#define BAR(i) (sb + M_BAR + 8 * (i))
#define kh (j & 1)
            int sl = 0;
#pragma unroll 1
            for (int s = 0; s < 28; s++) {
                if (s == 7) { wait_flags(g_flag + (8 * r + j) * 128 + 96 + lane, lds1(sb + M_EPOCH) + 1, 0xFFFFu); fence_async_global(); }
                const int ps = s < 14 ? 0 : s < 21 ? 1 : 2;
                const uint32_t half = ps < 2 ? 8192 : 4096;
                const int sp = sl;
                if (s >= PACE && s < PACE_END) mbar_wait(BAR(B_FULL + s - PACE), 0);
                mbar_wait(BAR(B_EMPTY + sp), (s >= 7 && s < 14) || s >= 21);
                expect_e(BAR(B_FULL + sp), half);
                tma3_e(sb + slot_off(sp) + sec * half, gmap + 2 * ps, 0, ps ? 64 * sl : 32 * s, ps == 0 ? fa >> 6 : ps == 1 ? fb >> 6 : fc >> 5, BAR(B_FULL + sp));
                sl = sl == 6 ? 0 : sl + 1;
            }
            if (!sec) PROFH(3);
#pragma unroll 1
            for (int e = 0; e < 4; e++) {
                const uint32_t dst = sb + slot_off(e) + sec * 8192, bar = BAR(B_FULL + e);
                const int f = (e < 2 ? fa + 64 * e : e == 2 ? fb : fc) + 32 * sec;
                mbar_wait(BAR(B_EMPTY + e), 0);
                expect_e(bar, e == 3 && sec ? 0 : 7168);
                if (!(e == 3 && sec)) { LOADW }
            }
            sl = 4;
            int e = 4;
#pragma unroll 1
            for (int grp = 0; grp < 9; grp++) {
                const int ps = grp >= 6 ? 2 : grp >= 3 ? 1 : 0;
                int sidx = grp - 3 * ps;
                if (sec && sidx == 0) { mbar_wait(BAR(B_HRDY + ps), 0); fence_async_global(); }
                sidx += sidx >= nq;
                int f = pass_f(4 * kh + sidx, ps);
#pragma unroll 1
                for (int k = 4 >> ps; k > 0; k--, e++, f += 32) {
                    const uint32_t dst = sb + slot_off(sl), bar = BAR(B_FULL + sl);
                    mbar_wait(BAR(B_EMPTY + sl), e >= 12 && e < 24);
                    if (e < WIN_END && e >= WIN) mbar_wait(BAR(B_FULL + (sl >= WIN ? sl - WIN : sl + 12 - WIN)), e - WIN >= 12);
                    expect_e(bar, sec ? 8192 : 7168);
                    if (!sec) { LOADW }
                    else bulk_e(dst + 8192, h2src + f * 64, 8192, bar);
                    sl = sl == 11 ? 0 : sl + 1;
                }
            }
            if (!sec) PROFH(4);
}

#define PROF_PARAMS
#define PROF_ARGS
__device__ __noinline__ void helper_late(const Params& p, int r_, int j_, int warp_ PROF_PARAMS) {
    extern __shared__ __align__(1024) unsigned char smem[];
    const uint32_t sb = (uint32_t)__cvta_generic_to_shared(smem);
    const int r = opaque(r_), j = opaque(j_), warp = opaque(warp_), nq = j >> 1, b = 8 * r + j;
    uint32_t* const act = (uint32_t*)__shfl_sync(~0u, (unsigned long long)(p.actb + (size_t)r * RB_WORDS), 0);
    {
        const int lane = fresh_tid() & 31;
        const uint32_t target = lds1(sb + M_EPOCH) + 1;
        if (warp == 8) { expect_e(BAR(B_XCH), 14336); expect_e(BAR(B_XCH + 1), 14336); }
            if (warp == 9) {
#pragma unroll 1
                for (int kv = 0; kv < 2; kv++) {
                    mbar_wait(BAR(B_PUB + kv), 0);
                    wait_flags(g_flag + b * 128 + lane, target, (r >= 2 ? 6u : r == 1 ? 2u : 0u) << (8 * kv));
                    fence_async_global();
                    const uint32_t dst = sb + OFF_Y + (kv ? Y_VR : Y_K);
                    expect_e(BAR(B_KRFULL + kv), r >= 2 ? 28672 : r == 1 ? 14336 : 0);
                    if (r >= 2) bulk_e(dst, act - 2 * RB_WORDS + RB_KV + j * 7168 + kv * 3584, 14336, BAR(B_KRFULL + kv));
                    if (r >= 1) bulk_e(dst + 14336, act - RB_WORDS + RB_KV + j * 7168 + kv * 3584, 14336, BAR(B_KRFULL + kv));
                    if (kv == 0) { PROFH(8); }
                }
            } else if (warp == 8) {
                uint4 v[8];
                mbar_wait(BAR(B_WOFULL), 0);
#pragma unroll
                for (int k = 0; k < 8; k++) v[k] = ld_relaxed4(mod_src(lane + 32 * k, r, j, true));
#pragma unroll
                for (int k = 0; k < 8; k++) mod_store(sb, v[k], mod_src(lane + 32 * k, r, j, true), lane + 32 * k);
                warp_arrive(BAR(B_MOD1));
            } else if (warp == 11) {
                if (kh == 1 && r < 14) {
                    const uint32_t wmbuf = sb + OFF_X + HALF;
                    const int mcol = 2 * DM + 32 * (4 * r + nq);
                    mbar_wait(BAR(B_XFREE), 0);
                    tma3_e(wmbuf, &p.wm2, mcol, 0, 0, BAR(B_WMFULL));
                    tma3_e(wmbuf + 14336, &p.wm2, mcol, 224, 0, BAR(B_WMFULL));
#pragma unroll 1
                    for (int wd = lane; wd < 224; wd += 32) {
                        const uint32_t cb = __ldg((const uint32_t*)p.c + wd);
                        sts1(wmbuf + 28672 + (wd >> 3) * 32 + (wd & 3) * 8 + (wd & 4), pack2(silu_bf(cb & 0xFFFFu), silu_bf(cb >> 16)));
                    }
                    __syncwarp();
                    mbar_wait(BAR(B_WMFULL), 0);
                    const uint32_t wa = wmbuf + (8 * (lane >> 4) + (lane & 7)) * 64 + ((lane >> 3) & 1) * 16;
                    float d[2][4] = {};
#pragma unroll 4
                    for (int ks = 0; ks < 28; ks++) {
                        uint32_t A[8];
                        ldsm4t(wa + ks * 1024, A); ldsm4t(wa + ks * 1024 + 32, A + 4);
                        const float2 v = lds2f(wmbuf + 28672 + ks * 32 + (lane & 3) * 8);
                        mma16816(d[0], A[0], A[1], A[2], A[3], __float_as_uint(v.x), __float_as_uint(v.y));
                        mma16816(d[1], A[4], A[5], A[6], A[7], __float_as_uint(v.x), __float_as_uint(v.y));
                    }
                    const int q = lane & 3, col = mcol + 8 * q + (lane >> 2);
                    const uint32_t word = mod_word(q == 0 ? d[0][0] : q == 1 ? d[0][2] : q == 2 ? d[1][0] : d[1][2], col, target);
#pragma unroll
                    for (int i = 0; i < 8; i++) st_relaxed(g_mod + i * 6 * DM + col, word);
                }
                warp_arrive(BAR(B_WMFREE));
                mbar_wait(BAR(B_VRFULL), 0);
                l2_prefetch_e((const char*)p.wg + (size_t)b * 12544, 12544);
                l2_prefetch_e((const char*)p.wu + (size_t)b * 12544, 12544);
#pragma unroll 1
                for (int k = 0; k < (r < 12 ? 2 : 1); k++) {
                    const int u = 28 * kh + r + 16 * k;
                    expect_e(BAR(B_XFULL + k), 7168);
                    tma3_e(sb + OFF_Y + 102400, &p.dn, 0, 32 * u, 7 * j, BAR(B_XFULL + k));
                    tma3_e(sb + OFF_Y + 102400 + 3584, &p.dn, 0, 32 * u, 7 * (j ^ 1), BAR(B_XFULL + k));
                    mbar_wait(BAR(B_XFULL + k), 1);
                    asm volatile("{\n.reg .pred p;\nelect.sync _|p, 0xffffffff;\n@p cp.async.bulk.global.shared::cta.bulk_group [%0], [%1], 7168;\n"
                                 "cp.async.bulk.commit_group;\ncp.async.bulk.wait_group 0;\n}" ::"l"(g_wd + (size_t)(u * 4 + nq) * 1792), "r"(sb + OFF_Y + 102400) : "memory");
                    __syncwarp();
                }
                warp_arrive(BAR(B_FULLK));
                fence_gpu();
                if (lane < 16) st_relaxed(g_flag + (8 * lane + j) * 128 + 96 + r, target);
            }
        if (warp == 8 || warp == 11) {
            const int sec = warp == 11;
            if (sec) ring_loader<1>(p, sb, r, j, lane); else ring_loader<0>(p, sb, r, j, lane);
            mbar_wait(BAR(B_DONE), 0);
        } else if (warp == 9) {
#pragma unroll
            for (int ev = 0; ev < 4; ev++) { expect_e(BAR(B_GFULL + ev), ev < 2 ? HALF / 2 : 16384 + 4096); expect_e(BAR(B_XFULL + 2 + ev), ev < 2 ? HALF / 2 : HALF - 16384); }
            mbar_wait(BAR(B_PUB + 2), 0);
            const uint32_t* fp = g_flag + b * 128 + 32 + lane;
            const int par = (target - 1) & 1;
#pragma unroll 1
            for (int n = 0, ev = 0; ev < 4; n++) {
                if (ev == 1) mbar_wait(BAR(B_PUB + 3), 0);
                uint32_t ok = __ballot_sync(~0u, (int)(ld_relaxed(fp) - target) >= 0) >> (8 * ev);
                while ((ok & 0xFFu) == 0xFFu) {
                    if (ev == 1) mbar_wait(BAR(B_FULLK), 1);
                    asm volatile("fence.acquire.gpu;" ::: "memory");
                    fence_async_global();
                    const int tile = (ev & 1) + (ev >> 1) * par * 2;
                    const uint32_t dst = sb + (ev == 0 ? OFF_X : OFF_Y + (ev & 1) * HALF), first = ev < 2 ? HALF / 2 : 16384;
                    const char* src = (const char*)(act + RB_O + ((ev >> 1) * 2 + tile) * 14336);
                    if (ev >= 2) bulk_e(sb + OFF_X + X_STAT + (ev & 1) * 49152, act + RB_ST + tile * 1024, 4096, BAR(B_GFULL + ev));
                    bulk_e(dst, src, first, BAR(B_GFULL + ev));
                    bulk_e(dst + first, src + first, HALF - first, BAR(B_XFULL + 2 + ev));
                    if (ev) PROFH(4 + ev);
                    ev++; ok >>= 8;
                }
                if (n > SPIN_LIMIT) __trap();
            }
            mbar_wait(BAR(B_XFULL + 5), 1);
#pragma unroll 1
            for (int hf = 0; hf < 2; hf++) {
                const int tile = (par ^ 1) * 2 + hf;
                uint4* xz = (uint4*)(act + RB_X1 + tile * 14336 + j * 1792) + lane;
#pragma unroll
                for (int i = 0; i < 14; i++) xz[i * 32] = make_uint4(0, 0, 0, 0);
                ((uint4*)(act + RB_ST + (tile * 8 + j) * 128))[lane] = make_uint4(0, 0, 0, 0);
            }
#pragma unroll 1
            for (int ps = 0; ps < 3; ps++) {
                mbar_wait(BAR(B_PUB + 6 + ps), 0);
                wait_flags(g_flag + b * 128 + 64 + lane, target, (0x55u << kh) << (8 * ps));
                warp_arrive(BAR(B_HRDY + ps));
                PROFH(9 + ps);
            }
        } else {
#pragma unroll 1
            for (int k = 0; k < 9; k++) {
                uint32_t* fp = k < 2 ? g_flag + (b + 8 * lane) * 128 + k * 8 + lane : g_flag + (8 * r + lane) * 128 + 16 + k * 8 + j;
                mbar_wait(BAR(B_PUB + k), 0);
                if (k != 4 && k != 5) fence_gpu();
                if (k < 2 ? (lane == 1 || lane == 2) : lane < 8) st_relaxed(fp, target);
                if (k >= 3 && k <= 5) PROFH(k - 3);
            }
        }
    }
}

__global__ void __cluster_dims__(2, 1, 1) __launch_bounds__(384, 1) fused_block_kernel(const __grid_constant__ Params p) {
    extern __shared__ __align__(1024) unsigned char smem[];
    const uint32_t sb = (uint32_t)__cvta_generic_to_shared(smem);
    const int tid = threadIdx.x, lane = tid & 31, warp = __shfl_sync(~0u, tid >> 5, 0);
    const int m = blockIdx.x >> 1;
    int r, nq;
    if (m < 4) { r = 15; nq = m; }
    else if (m < 36) { r = (m - 4) & 7; nq = (m - 4) >> 3; }
    else { nq = (m - 36) / 7; r = m - 28 - 7 * nq; }
    const int j = opaque(2 * nq + (blockIdx.x & 1)), b = 8 * r + j, fs = 4 * kh + nq;
#define act (p.actb + (size_t)r * RB_WORDS)
    constexpr uint32_t sc = 0;
    if (lane == 0 && warp < 9 && warp != 6 && warp != 7) {
        const int i0 = warp == 8 ? 0 : 8 + 8 * warp, cnt = warp == 0 || warp == 8 ? 1 : warp < 3 ? 2 : 8;
#pragma unroll
        for (int k = 0; k < 8; k++) if (i0 + k != B_WMFULL) mbar_init(BAR(i0 + k), cnt);
        if (warp == 8) mbar_init(BAR(B_WMFULL), 1);
        asm volatile("fence.mbarrier_init.release.cluster;" ::: "memory");
        fence_async_smem();
    }

    if (warp >= 8) {
        const int lane = fresh_tid() & 31;
        const bool early = kh == 0, gemv = r < 14;
        const int mcol = early ? 16 * (4 * r + nq) : 2 * DM + 32 * (4 * r + nq);
        const uint32_t wmbuf = sb + OFF_Y + HALF;
        if (warp == 8) {
            __syncwarp();
            expect_e(BAR(B_WMFULL), gemv ? 28672 >> early : 0);
            if (early && gemv) { tma3_e(wmbuf, &p.wm, mcol, 0, 0, BAR(B_WMFULL)); tma3_e(wmbuf + 7168, &p.wm, mcol, 224, 0, BAR(B_WMFULL)); }
#pragma unroll
            for (int kb = 0; kb < XFIRST; kb++) {
                expect_e(BAR(B_XFULL + kb), 16384);
                tma3_e(sb + OFF_X + kb * 16384, &p.xm, 64 * kb, 128 * r, 0, BAR(B_XFULL + kb));
            }
        }
        asm volatile("setmaxnreg.dec.sync.aligned.u32 56;");
        if (warp == 9) {
#pragma unroll
            for (int i = 56; i < 64; i++) init_e(BAR(i), 1);
            fence_async_smem();
        }
        bar_arrive(0, 384);
        asm volatile("barrier.cluster.arrive.relaxed.aligned;" ::: "memory");
        if (warp == 8) {
#pragma unroll
            for (int kb = XFIRST; kb < 7; kb++) {
                expect_e(BAR(B_XFULL + kb), 16384);
                tma3_e(sb + OFF_X + kb * 16384, &p.xm, 64 * kb, 128 * r, 0, BAR(B_XFULL + kb));
            }
            if (KDELAY >= 0) { mbar_wait(BAR(B_XFULL + KDELAY), 0); l2_prefetch_e((const char*)p.wqkv + (size_t)b * 9408, 9408); }
#pragma unroll 1
            for (int mt = 0; mt < 4; mt++) {
                if (mt == 1) bar_sync(9, 384);
                if (mt == 3) mbar_wait(BAR(B_WMFREE), 0);
                if (mt) mbar_wait(BAR(mt == 1 ? B_MOD1 : mt == 2 ? B_XFREE : B_VRFULL), 0);
                const uint32_t bar = BAR(mt == 3 ? B_WOFULL : B_FULLK + mt), dst = sb + (mt < 2 ? OFF_Y : OFF_X) + (mt & 1) * HALF;
                const int c0 = (mt < 2 ? DM + DM * mt : 0) + 56 * j - 8 * kh;
                if (!sc) {
                    expect_e(bar, HALF);
                    tma3_e(dst, mt == 3 ? &p.wo : &p.qkv, c0, 0, 0, bar);
                    tma3_e(dst + HALF / 2, mt == 3 ? &p.wo : &p.qkv, c0, 224, 0, bar);
                }
            }
        } else {
            if (KDELAY < 0 && warp == 10) l2_prefetch_e((const char*)p.wqkv + (size_t)b * 9408, 9408);
            bar_sync(9, 384);
            if (sc) return;
            if (warp == 11 && early) {
                const uint32_t target = lds1(sb + M_EPOCH) + 1;
                mbar_wait(BAR(B_GEMV), 0);
                float sum = 0.f;
#pragma unroll
                for (int i = 0; i < 8; i++) sum += *(const float*)(smem + OFF_Y + HALF + 29696 + (i * 16 + (lane & 15)) * 4);
                uint32_t* mg = g_mod + mcol + (lane & 15) + (lane >> 4) * 4 * 6 * DM;
                const uint32_t word = mod_word(sum, mcol, target);
                if (gemv) { st_relaxed(mg, word); st_relaxed(mg + 6 * DM, word); st_relaxed(mg + 12 * DM, word); st_relaxed(mg + 18 * DM, word); }
            }
        }
    }
    if (LIKELY(warp < 8)) {
        const int w = warp >> 2, wi = warp & 3;
#define COORDS const int t = fresh_tid() & 127, lane = t & 31, q = lane & 3, lr = lane >> 2, ra = 64 * w + 16 * wi + lr; \
        const uint32_t lx = (lane >> 4) ^ (lane & 7), mrow = (64 * w + 16 * wi + ((lane >> 3) & 1) * 8 + (lane & 7)) * 128; \
        (void)q; (void)lr; (void)ra; (void)lx; (void)mrow;
        const int sid = 2 * (j & 3) + w;
#define RUN(k) (!sc || sid == (k))
#define WAIT(i, par) mbar_wait_c(BAR(i), (par) | sc)
        constexpr uint64_t DB128 = dconst(4096, 1024, 1);
        {
            const int wd = fresh_tid();
            const uint32_t cb = wd < 224 ? __ldg((const uint32_t*)p.c + wd) : 0u;
            if (wd == 255 && !sc) sts1(sb + M_EPOCH, atomicAdd(&g_ticket, 1u) / NCTA);
            sts1(sb + OFF_Y + HALF + 28672 + (wd >> 3) * 32 + (wd & 3) * 8 + (wd & 4), pack2(silu_bf(cb & 0xFFFFu), silu_bf(cb >> 16)));
        }
        bar_arrive(9, 384);
        bar_sync(0, 384);
        asm volatile("barrier.cluster.arrive.relaxed.aligned;" ::: "memory");
        asm volatile("setmaxnreg.inc.sync.aligned.u32 224;");
        PROFC(0);
        uint32_t xr[16];
        {
            COORDS
            uint32_t h[112];
            uint32_t ra2, na2, rb2, nb2;
            const int mi = min(128 * w + t, 223);
            const uint4* msrc = mod_src(mi, r, j, false);
            uint4 mv;
            {
                float ds[4] = {}, da[2][4] = {}, db[2][4] = {};
                const uint32_t ONE2 = 0x3F803F80u;
#pragma unroll
                for (int kb = 0; kb < 7; kb++) {
                    if (kb == GEMV_AT && kh == 0) { WAIT(B_WMFULL, 0); gemv_part(sb + OFF_Y + HALF, warp, lane); warp_arrive(BAR(B_GEMV)); }
                    WAIT(B_XFULL + kb, 0);
#pragma unroll
                    for (int k4 = 0; k4 < 4; k4++) ldsm4(sb + OFF_X + mrow + kb * 16384 + (((2 * k4) ^ lx) << 4), h + 16 * kb + 4 * k4);
#pragma unroll
                    for (int k4 = 0; k4 < 4; k4++) {
                        const uint32_t* f = h + 16 * kb + 4 * k4;
                        mma16816(ds, f[0], f[1], f[2], f[3], ONE2, ONE2);
                        mma1688(da[0], f[0], f[1], f[0]); mma1688(db[0], f[0], f[1], f[1]);
                        mma1688(da[1], f[2], f[3], f[2]); mma1688(db[1], f[2], f[3], f[3]);
                    }
                }
#pragma unroll
                for (int i = 0; i < 4; i++) {
                    const int ch = 7 * j + 2 * i + (lane >> 4);
                    ldsm4(sb + OFF_X + mrow + (ch >> 3) * 16384 + (((ch ^ lane) & 7) << 4), xr + 4 * i);
                }
                mv = ld_relaxed4(msrc);
                warp_arrive(BAR(B_XFREE));
                float qa = (lr & 1) ? da[0][1] + da[1][1] : da[0][0] + da[1][0];
                float qb = (lr & 1) ? db[0][3] + db[1][3] : db[0][2] + db[1][2];
                const int src = (lane & ~3) | (lr >> 1);
                qa = __shfl_sync(~0u, qa, src);
                qb = __shfl_sync(~0u, qb, src);
                ln_coeffs(ds[0] * (1.f / DM), qa * (1.f / DM), ra2, na2);
                ln_coeffs(ds[2] * (1.f / DM), qb * (1.f / DM), rb2, nb2);
#pragma unroll
                for (int i = 0; i < 4 * NPRE; i += 2) { h[i] = hfma2(h[i], ra2, na2); h[i + 1] = hfma2(h[i + 1], rb2, nb2); }
            }
            PROFC(1);
            {
                float ak[28], av[28], aq[28];
                uint32_t kp[14], vp[14];
                const uint64_t bq0 = (DB128 & ~0xFFFFFFFFull) | (mkdesc(sb + OFF_X, DB128) + kh), bk0 = bq0 + (OFF_Y >> 4), bv0 = bk0 + (HALF >> 4);
                uint32_t* kvg = act + RB_KV + j * 7168 + (8 * w + 2 * wi) * 224 + lane;
                mod_store(sb, mv, msrc, mi);
                bar_sync(3, 256);
                if (warp == 0) warp_arrive(BAR(B_MOD1));
                WAIT(B_FULLK, 0);
                PROFC(2);
                reg_def<28>(ak);
#pragma unroll
                for (int g4 = 0; g4 < 4; g4++) {
#pragma unroll
                    for (int ks = 7 * g4; ks < 7 * g4 + 7; ks++) {
                        const uint4 st = *(const uint4*)(smem + M_ST + ks * 64 + q * 16);
                        if (ks >= NPRE) {
                            h[4 * ks] = hfma2(h[4 * ks], ra2, na2); h[4 * ks + 1] = hfma2(h[4 * ks + 1], rb2, nb2);
                            h[4 * ks + 2] = hfma2(h[4 * ks + 2], ra2, na2); h[4 * ks + 3] = hfma2(h[4 * ks + 3], rb2, nb2);
                        }
                        h[4 * ks] = hfma2(h[4 * ks], st.x, st.y); h[4 * ks + 1] = hfma2(h[4 * ks + 1], st.x, st.y);
                        h[4 * ks + 2] = hfma2(h[4 * ks + 2], st.z, st.w); h[4 * ks + 3] = hfma2(h[4 * ks + 3], st.z, st.w);
                    }
                    WG_FENCE();
#pragma unroll
                    for (int ks = 7 * g4; ks < 7 * g4 + 7; ks++) wgmma_rl_56(ak, h[4 * ks], h[4 * ks + 1], h[4 * ks + 2], h[4 * ks + 3], bk0 + ks * 128, ks != 0);
                }
                WG_COMMIT();
                PROFC(3);
                reg_def<28>(av);
                WG_WAIT(0);
                reg_fence<28>(ak);
#pragma unroll
                for (int g = 0; g < 7; g++) {
                    kp[2 * g] = pack2(ak[4 * g], ak[4 * g + 1]); kp[2 * g + 1] = pack2(ak[4 * g + 2], ak[4 * g + 3]);
                    kvg[g * 32] = kp[2 * g]; kvg[224 + g * 32] = kp[2 * g + 1];
                }
                warp_arrive(BAR(B_PUB));
                PROFC(4);
                if (KEARLY) WAIT(B_FULLV, 0);
                WG_FENCE();
#pragma unroll
                for (int ks = KEARLY ? 0 : 8; ks < 28; ks++) wgmma_rl_56(av, h[4 * ks], h[4 * ks + 1], h[4 * ks + 2], h[4 * ks + 3], bv0 + ks * 128, ks != 0);
                WG_COMMIT();
                reg_def<28>(aq);
                WAIT(B_FULLQ, 0);
                WG_FENCE();
#pragma unroll
                for (int ks = 0; ks < VPRE; ks++) wgmma_rl_56(aq, h[4 * ks], h[4 * ks + 1], h[4 * ks + 2], h[4 * ks + 3], bq0 + ks * 128, ks != 0);
                WG_COMMIT();
                WG_WAIT(1);
                reg_fence<28>(av);
#pragma unroll
                for (int g = 0; g < 7; g++) {
                    vp[2 * g] = pack2(av[4 * g], av[4 * g + 1]); vp[2 * g + 1] = pack2(av[4 * g + 2], av[4 * g + 3]);
                    kvg[3584 + g * 32] = vp[2 * g]; kvg[3584 + 224 + g * 32] = vp[2 * g + 1];
                }
                warp_arrive(BAR(B_PUB + 1));
                PROFC(5);
                if (!VPRE) WAIT(B_FULLQ, 0);
                WG_FENCE();
#pragma unroll
                for (int ks = VPRE; ks < 28; ks++) wgmma_rl_56(aq, h[4 * ks], h[4 * ks + 1], h[4 * ks + 2], h[4 * ks + 3], bq0 + ks * 128, ks != 0);
                WG_COMMIT();
                WAIT(B_PUB + 1, 0);
                const uint32_t rg = 8 * w + 2 * wi + ((lane >> 3) & 1);
                const uint32_t ko = sb + OFF_Y + Y_KOWN + rg * 896 + (lane & 7) * 16, qo = sb + OFF_Y + Y_Q + rg * 1024 + (lane >> 4) * 128 + (lane & 7) * 16;
#pragma unroll
                for (int g = 0; g < 6; g += 2) {
                    stsm4(ko + (g + (lane >> 4)) * 128, kp[2 * g], kp[2 * g + 1], kp[2 * g + 2], kp[2 * g + 3]);
                    stsm4(ko + (Y_VOWN - Y_KOWN) + (g + (lane >> 4)) * 128, vp[2 * g], vp[2 * g + 1], vp[2 * g + 2], vp[2 * g + 3]);
                }
                stsm4(ko + (lane >> 4) * (Y_VOWN - Y_KOWN) + 6 * 128, kp[12], kp[13], vp[12], vp[13]);
                WG_WAIT(0);
                reg_fence<28>(aq);
                __syncwarp();
                if (lane < 3 && w == 1) mbar_arrive(BAR(B_EMPTY + lane));
                uint32_t qp[14];
#pragma unroll
                for (int i = 0; i < 14; i++) qp[i] = pack2(aq[2 * i], aq[2 * i + 1]);
                stsm4(qo, qp[0], qp[1], qp[2], qp[3]);
                stsm4(qo + 256, qp[4], qp[5], q < 2 ? qp[6] : 0u, q < 2 ? qp[7] : 0u);
                stsm4(qo + 512, q < 2 ? 0u : qp[6], q < 2 ? 0u : qp[7], qp[8], qp[9]);
                stsm4(qo + 768, qp[10], qp[11], qp[12], qp[13]);
                fence_async_smem();
                if (!sc) bar_sync(3, 256);
            }
        }
        PROFC(6);
        WAIT(B_KRFULL, 0);
        if (ATT_OFF && w == ATT_WG) { const uint32_t t0 = clock(); while (clock() - t0 < ATT_OFF) {} }
        PROFC(7);
        if (RUN(2)) {
#pragma unroll 1
            for (int hf = sc; hf < 2; hf++) {
                COORDS
                float s[160];
                const float CS = 0.18898223650461361f * 1.4426950408889634f;
                const float NEG = __int_as_float(0xFF800000);
                constexpr uint64_t DQ = dconst(128, 1024, 0), DK = dconst(128, 896, 0);
                {
                    const uint32_t qd = mkdesc(sb + OFF_Y + Y_Q + hf * 8192 + w * 512, DQ), kd = mkdesc(sb + OFF_Y + Y_K + hf * 8 * 896 + w * 384, DK);
                    reg_def<160>(s);
                    WG_FENCE();
                    wgmma_sk_160<DQ, DK>(s, qd, kd, 0);
                    wgmma_sk_160<DQ, DK>(s, qd + 16, kd + 16, 1);
                    wgmma_sk_160<DQ, DK>(s + 80, qd, kd + 20 * 56, 0);
                    wgmma_sk_160<DQ, DK>(s + 80, qd + 16, kd + 20 * 56 + 16, 1);
                    WG_COMMIT();
                    WG_WAIT(0);
                    reg_fence<160>(s);
                }
                if (r < 2) {
                    const int pmin = 4 - 2 * r - hf;
#pragma unroll
                    for (int p4 = 0; p4 < 4; p4++)
                        if (p4 < pmin) {
#pragma unroll
                            for (int i = 0; i < 32; i++) asm volatile("mov.b32 %0, 0xFF800000;" : "=f"(s[32 * p4 + i]));
                        }
                }
                const bool c0 = 2 * q > lr, c1 = 2 * q + 1 > lr;
#pragma unroll
                for (int pp = 0; pp < 4; pp++) {
                    const bool me = pp == wi;
                    float* e = s + 8 * pp;
                    if (me && !c0) { e[0] = NEG; e[6] = NEG; }
                    if (me && !c1) { e[1] = NEG; e[7] = NEG; }
                    if (me) { e[2] = NEG; e[3] = NEG; }
                    e = s + 8 * (pp + 16);
                    if (me && c0) { e[0] = NEG; e[6] = NEG; }
                    if (me && c1) { e[1] = NEG; e[7] = NEG; }
                    if (me) { e[4] = NEG; e[5] = NEG; }
                }
#pragma unroll
                for (int i = 0; i < 24; i++) s[i] = (i >> 3) < wi ? s[136 + i] : s[i];
                int i0 = 0x80000000, i1 = 0x80000000, i2 = 0x80000000, i3 = 0x80000000;
#pragma unroll
                for (int pp = 0; pp < 17; pp++) {
                    const float* e = s + 8 * pp;
                    i0 = __vimax3_s32(i0, __float_as_int(e[0]), __float_as_int(e[1])); i1 = __vimax3_s32(i1, __float_as_int(e[2]), __float_as_int(e[3]));
                    i2 = __vimax3_s32(i2, __float_as_int(e[4]), __float_as_int(e[5])); i3 = __vimax3_s32(i3, __float_as_int(e[6]), __float_as_int(e[7]));
                }
                i0 = max(i0, i2); i1 = max(i1, i3);
                i0 = max(i0, __shfl_xor_sync(~0u, i0, 1)); i1 = max(i1, __shfl_xor_sync(~0u, i1, 1));
                i0 = max(i0, __shfl_xor_sync(~0u, i0, 2)); i1 = max(i1, __shfl_xor_sync(~0u, i1, 2));
                if (__any_sync(~0u, (i0 | i1) < 0)) {
                    uint32_t u0 = ~0u, u1 = ~0u, u2 = ~0u, u3 = ~0u;
#pragma unroll
                    for (int pp = 0; pp < 17; pp++) {
                        const float* e = s + 8 * pp;
                        u0 = __vimin3_u32(u0, __float_as_uint(e[0]), __float_as_uint(e[1])); u1 = __vimin3_u32(u1, __float_as_uint(e[2]), __float_as_uint(e[3]));
                        u2 = __vimin3_u32(u2, __float_as_uint(e[4]), __float_as_uint(e[5])); u3 = __vimin3_u32(u3, __float_as_uint(e[6]), __float_as_uint(e[7]));
                    }
                    u0 = min(u0, u2); u1 = min(u1, u3);
                    u0 = min(u0, __shfl_xor_sync(~0u, u0, 1)); u1 = min(u1, __shfl_xor_sync(~0u, u1, 1));
                    u0 = min(u0, __shfl_xor_sync(~0u, u0, 2)); u1 = min(u1, __shfl_xor_sync(~0u, u1, 2));
                    if (i0 < 0) i0 = u0;
                    if (i1 < 0) i1 = u1;
                }
                const float ma = __int_as_float(i0), mb = __int_as_float(i1);
                const float na = -ma * CS, nb = -mb * CS;
                PROFC(8 + 3 * hf);
                {
                    WAIT(B_VRFULL, 0);
                    float o[16] = {}, rs[4] = {};
                    const uint32_t va = sb + OFF_Y + Y_VR + (8 * hf + ((lane >> 3) & 1)) * 896 + (3 * w + (lane >> 4)) * 128 + (lane & 7) * 16;
                    constexpr uint32_t OWN = Y_VOWN - 32 * 896;
#pragma unroll
                    for (int pp = 0; pp < 17; pp++) {
                        uint32_t B[8];
                        const uint32_t v = va + pp * 1792 + (pp < 3 ? (pp < wi ? 17 * 1792 + OWN : 0) : pp == 16 ? OWN : pp >= 12 ? hf * OWN : 0);
                        ldsm4t(v, B); ldsm4t(v + 256, B + 4);
                        float e[8];
#pragma unroll
                        for (int i = 0; i < 8; i++) e[i] = ex2(fmaf(s[8 * pp + i], CS, (i & 2) ? nb : na));
                        const uint32_t p0 = pack2(e[0], e[1]), p1 = pack2(e[2], e[3]), p2 = pack2(e[4], e[5]), p3 = pack2(e[6], e[7]);
                        mma16816(rs, p0, p1, p2, p3, 0x3F803F80u, 0x3F803F80u);
#pragma unroll
                        for (int g = 0; g < 4; g++) mma16816(o + 4 * g, p0, p1, p2, p3, B[2 * g], B[2 * g + 1]);
                    }
                    PROFC(9 + 3 * hf);
                    const float ia = rcp(rs[0]), ib = rcp(rs[2]);
                    uint32_t* og = act + RB_O + hf * 14336 + (7 * j + 3 * w) * 256 + wi * 64 + lane;
#pragma unroll
                    for (int g = 0; g < 4; g++) {
                        if ((g == 3 - 3 * w) ? ((q >> 1) == w) : true) {
                            og[g * 256] = pack2(o[4 * g] * ia, o[4 * g + 1] * ia);
                            og[g * 256 + 32] = pack2(o[4 * g + 2] * ib, o[4 * g + 3] * ib);
                        }
                    }
                    warp_arrive(BAR(B_PUB + 2 + hf));
                    PROFC(10 + 3 * hf);
                }
            }
        }
        uint32_t x1p[14];
        COORDS
        constexpr uint64_t DT = dconst(1024, 128, 0);
        const int tile = opaque((lds1(sb + M_EPOCH) & 1) * 2 + w);
        if (RUN(4)) {
            float ac[28];
            const uint32_t ad = mkdesc(sb + (w ? OFF_Y + HALF : OFF_X), DT), bd = mkdesc(sb + OFF_X + HALF, DB128) + kh;
            WAIT(B_WOFULL, 0);
            WAIT(B_MOD1, 1);
            WAIT(B_GFULL + w, 0);
            PROFC(28);
            reg_def<28>(ac);
#pragma unroll 1
            for (int u = 0; u < 4; u++) {
                if (u == 2) WAIT(B_XFULL + 2 + w, 1);
                WG_FENCE();
#pragma unroll
                for (int i = 0; i < 7; i++) wgmma_ss_56<DT, DB128>(ac, ad + (7 * u + i) * 128, bd + (7 * u + i) * 128, (u | i) != 0);
            }
            WG_COMMIT();
            WG_WAIT(0);
            reg_fence<28>(ac);
            PROFC(14);
            __syncwarp();
            if (lane < 3) mbar_arrive(BAR(B_EMPTY + 4 - w + lane));
            if (lane < 3 && w == 0) mbar_arrive(BAR(B_EMPTY + lane));
            float ds[4] = {}, da[4] = {}, db[4] = {};
            uint32_t* xo = act + RB_X1 + tile * 14336 + 7 * j * 256 + wi * 64 + lane;
#pragma unroll
            for (int g = 0; g < 7; g++) {
                const float2 ga = *(const float2*)(smem + M_G + (8 * g + 2 * q) * 4);
                x1p[2 * g] = pack2(fmaf(ga.x, ac[4 * g], bf_lo(xr[2 * g])), fmaf(ga.y, ac[4 * g + 1], bf_hi(xr[2 * g])));
                x1p[2 * g + 1] = pack2(fmaf(ga.x, ac[4 * g + 2], bf_lo(xr[2 * g + 1])), fmaf(ga.y, ac[4 * g + 3], bf_hi(xr[2 * g + 1])));
                st_relaxed(xo + g * 256, nz(x1p[2 * g])); st_relaxed(xo + g * 256 + 32, nz(x1p[2 * g + 1]));
                mma1688(ds, x1p[2 * g], x1p[2 * g + 1], 0x3F803F80u);
                mma1688(da, x1p[2 * g], x1p[2 * g + 1], x1p[2 * g]);
                mma1688(db, x1p[2 * g], x1p[2 * g + 1], x1p[2 * g + 1]);
            }
            const int src = (lane & ~3) | (lr >> 1);
            const float qa = __shfl_sync(~0u, (lr & 1) ? da[1] : da[0], src), qb = __shfl_sync(~0u, (lr & 1) ? db[3] : db[2], src);
            const float kk = (q & 1) ? ((q & 2) ? qb : qa) : ((q & 2) ? ds[2] : ds[0]);
            st_relaxed(act + RB_ST + ((tile * 8 + j) * 64 + 16 * wi + lr + 4 * (q & 2)) * 2 + (q & 1), nz(__float_as_uint(kk)));
            __syncwarp();
            if (lane < 2) mbar_arrive(BAR(B_PUB + 4 + w));
        } else reg_def<14>(x1p);
        PROFC(15);
        uint32_t h2a[32], h2b[24];
        {
            const int fa = pass_f(fs, 0), fb = pass_f(fs, 1), fc = pass_f(fs, 2);
            uint32_t* h2g = act + RB_H2 + (8 * w + 2 * wi) * 32 + lane;
            const uint32_t a0 = mkdesc(sb + OFF_Y + w * HALF, DT);
            if (RUN(3)) {
                uint32_t ra2, na2, rb2, nb2;
                {
                    const uint32_t* sg = act + RB_ST + ((tile * 8 + 2 * q) * 64 + 16 * wi + lr) * 2;
                    uint2 u[4];
                    WAIT(B_GFULL + 2 + w, 0);
                    PROFC(16);
#pragma unroll
                    for (int i = 0; i < 4; i++) { const float2 v = lds2f(sb + OFF_X + X_STAT + w * 49152 + ((2 * q + (i >> 1)) * 64 + 16 * wi + lr + 8 * (i & 1)) * 8); u[i] = make_uint2(__float_as_uint(v.x), __float_as_uint(v.y)); }
                    while (__any_sync(~0u, min(min(min(u[0].x, u[0].y), min(u[1].x, u[1].y)), min(min(u[2].x, u[2].y), min(u[3].x, u[3].y))) < 1u - sc)) {
#pragma unroll
                        for (int i = 0; i < 4; i++) u[i] = ld_relaxed2(sg + (i >> 1) * 128 + (i & 1) * 16);
                    }
                    warp_arrive(BAR(B_EMPTY + 3 + 3 * w));
                    float v[4] = {__uint_as_float(u[0].x) + __uint_as_float(u[2].x), __uint_as_float(u[0].y) + __uint_as_float(u[2].y),
                                  __uint_as_float(u[1].x) + __uint_as_float(u[3].x), __uint_as_float(u[1].y) + __uint_as_float(u[3].y)};
#pragma unroll
                    for (int i = 0; i < 4; i++) { v[i] += __shfl_xor_sync(~0u, v[i], 1); v[i] += __shfl_xor_sync(~0u, v[i], 2); }
                    ln_coeffs(v[0] * (1.f / DM), v[1] * (1.f / DM), ra2, na2);
                    ln_coeffs(v[2] * (1.f / DM), v[3] * (1.f / DM), rb2, nb2);
                }
                const uint32_t ha = sb + OFF_Y + w * HALF + (lane >> 4) * 1024 + (2 * wi + ((lane >> 3) & 1)) * 128 + (lane & 7) * 16;
                const uint32_t sta = sb + M_ST + q * 16;
                const uint32_t* xg = act + RB_X1 + tile * 14336 + (lane >> 4) * 256 + wi * 64 + (lane & 15) * 4;
                uint32_t x[8];
                const uint32_t xs = sb + OFF_Y + w * HALF + (lane >> 4) * 1024 + wi * 256 + (lane & 15) * 16;
                uint4 st[2];
                auto load = [&](int s) {
                    if (s == 4) mbar_wait_c(BAR(B_XFULL + 4 + w), 1);
                    ldsm4(ha + s * 4096, x); ldsm4(ha + s * 4096 + 2048, x + 4);
                    st[0] = lds4(sta + s * 128); st[1] = lds4(sta + s * 128 + 64);
                };
                auto prep = [&](int s, uint32_t* f) {
                    if (__any_sync(~0u, min(min(min(x[0], x[1]), min(x[2], x[3])), min(min(x[4], x[5]), min(x[6], x[7]))) < 1u - sc)) {
                        WG_WAIT(0);
                        x1_fix(xg, xs, s);
                        ldsm4(ha + s * 4096, x); ldsm4(ha + s * 4096 + 2048, x + 4);
                    }
#pragma unroll
                    for (int i = 0; i < 2; i++) {
                        f[4 * i] = hfma2(hfma2(x[4 * i], ra2, na2), st[i].x, st[i].y); f[4 * i + 1] = hfma2(hfma2(x[4 * i + 1], rb2, nb2), st[i].x, st[i].y);
                        f[4 * i + 2] = hfma2(hfma2(x[4 * i + 2], ra2, na2), st[i].z, st[i].w); f[4 * i + 3] = hfma2(hfma2(x[4 * i + 3], rb2, nb2), st[i].z, st[i].w);
                    }
                    if (s < 13) load(s + 1);
                    stsm4(ha + s * 4096, f[0], f[1], f[2], f[3]); stsm4(ha + s * 4096 + 2048, f[4], f[5], f[6], f[7]);
                };
                float ac[128];
                uint32_t fr[3][8];
                uint64_t bd = (DB128 & ~0xFFFFFFFFull) | mkdesc(sb, DB128);
                reg_def<128>(ac);
                load(0);
                prep(0, fr[0]);
                PROFC(17);
#pragma unroll
                for (int s = 0; s < 14; s++) {
                    const uint32_t* f = fr[s % 3];
                    WAIT(B_FULL + g1_slot(s), s >= 7);
                    WG_FENCE();
                    wgmma_rl_256(ac, f[0], f[1], f[2], f[3], bd, s != 0);
                    wgmma_rl_256(ac, f[4], f[5], f[6], f[7], bd + 128, 1);
                    bd += s == 6 ? p.zero - 6 * 1024ull : 1024;
                    WG_COMMIT();
                    if (s < 13) prep(s + 1, fr[(s + 1) % 3]);
                    if (s > 0) { WG_WAIT(1); warp_arrive(BAR(B_EMPTY + g1_slot(s - 1))); }
                }
                fence_async_smem();
                PROFC(18);
                WG_WAIT(0);
                reg_fence<128>(ac);
                warp_arrive(BAR(B_EMPTY + 6));
#pragma unroll
                for (int g = 0; g < 16; g++) {
                    h2a[2 * g] = hmul2(pack2_relu(ac[4 * g], ac[4 * g + 1]), pack2(ac[64 + 4 * g], ac[64 + 4 * g + 1]));
                    h2a[2 * g + 1] = hmul2(pack2_relu(ac[4 * g + 2], ac[4 * g + 3]), pack2(ac[64 + 4 * g + 2], ac[64 + 4 * g + 3]));
                }
                bar_sync(1 + w, 128);
            } else reg_def<32>(h2a);
            PROFC(19);
            if (RUN(5)) {
                float ac[64];
                reg_def<64>(ac);
                const uint32_t bx = mkdesc(sb, dconst(8192, 1024, 1));
#pragma unroll kB
                for (int s = 0; s < 7; s++) {
                    WAIT(B_FULL + s, 0);
                    const uint32_t ad = a0 + s * 512, bd = bx + (slot_off(s) >> 4);
                    WG_FENCE();
#pragma unroll
                    for (int k = 0; k < 4; k++) wgmma_ss_128<DT, DB128>(ac, ad + k * 128, bd + k * 128, (s | k) != 0);
                    WG_COMMIT();
                    if (s == 1) {
#pragma unroll
                        for (int g = 0; g < 16; g++) { h2g[(fa / 8 + g) * 512] = h2a[2 * g]; h2g[(fa / 8 + g) * 512 + 32] = h2a[2 * g + 1]; }
                        warp_arrive(BAR(B_PUB + 6));
                    }
                    if (s > 0) { WG_WAIT(1); warp_arrive(BAR(B_EMPTY + s - 1)); }
                }
                WG_WAIT(0);
                reg_fence<64>(ac);
                warp_arrive(BAR(B_EMPTY + 6));
#pragma unroll
                for (int g = 0; g < 8; g++) {
                    h2b[2 * g] = hmul2(pack2_relu(ac[4 * g], ac[4 * g + 1]), pack2(ac[32 + 4 * g], ac[32 + 4 * g + 1]));
                    h2b[2 * g + 1] = hmul2(pack2_relu(ac[4 * g + 2], ac[4 * g + 3]), pack2(ac[32 + 4 * g + 2], ac[32 + 4 * g + 3]));
                }
            } else reg_def<16>(h2b);
            PROFC(27);
            if (RUN(6)) {
                float ac[32];
                reg_def<32>(ac);
                const uint32_t bx = mkdesc(sb, dconst(4096, 512, 2));
#pragma unroll kC
                for (int s = 0; s < 7; s++) {
                    WAIT(B_FULL + s, 1);
                    const uint32_t ad = a0 + s * 512, bd = bx + (slot_off(s) >> 4);
                    WG_FENCE();
#pragma unroll
                    for (int k = 0; k < 4; k++) wgmma_ss_64<DT, dconst(4096, 512, 2)>(ac, ad + k * 128, bd + k * 64, (s | k) != 0);
                    WG_COMMIT();
                    if (s == 1) {
#pragma unroll
                        for (int g = 0; g < 8; g++) { h2g[(fb / 8 + g) * 512] = h2b[2 * g]; h2g[(fb / 8 + g) * 512 + 32] = h2b[2 * g + 1]; }
                        warp_arrive(BAR(B_PUB + 7));
                    }
                    if (s > 0) { WG_WAIT(1); warp_arrive(BAR(B_EMPTY + s - 1)); }
                }
                WG_WAIT(0);
                reg_fence<32>(ac);
                __syncwarp();
                if (lane < 6) mbar_arrive(BAR(B_EMPTY + 6 + lane));
                PROFC(20);
#pragma unroll
                for (int g = 0; g < 4; g++) {
                    h2b[16 + 2 * g] = hmul2(pack2_relu(ac[4 * g], ac[4 * g + 1]), pack2(ac[16 + 4 * g], ac[16 + 4 * g + 1]));
                    h2b[16 + 2 * g + 1] = hmul2(pack2_relu(ac[4 * g + 2], ac[4 * g + 3]), pack2(ac[16 + 4 * g + 2], ac[16 + 4 * g + 3]));
                    h2g[(fc / 8 + g) * 512] = h2b[16 + 2 * g]; h2g[(fc / 8 + g) * 512 + 32] = h2b[16 + 2 * g + 1];
                }
                warp_arrive(BAR(B_PUB + 8));
                asm volatile("barrier.cluster.wait.aligned;" ::: "memory");
                if (lane == 0 && !sc) {
                    uint32_t rb;
                    asm volatile("mapa.shared::cluster.u32 %0, %1, %2;" : "=r"(rb) : "r"(BAR(B_PEER)), "r"(kh ^ 1));
                    asm volatile("mbarrier.arrive.relaxed.cluster.shared::cluster.b64 _, [%0];" ::"r"(rb) : "memory");
                }
            } else reg_def<8>(h2b + 16);
        }
        PROFC(21);
        if (RUN(7)) {
            float ac[56];
            reg_def<56>(ac);
            constexpr uint64_t DAN = dconst(2048, 128, 0);
            constexpr uint64_t DW = dconst(128, 512, 0);
            const uint32_t bx = mkdesc(sb, DW);
#pragma unroll
            for (int e = 0; e < 4; e++) {
                WAIT(B_FULL + e, 0);
                const uint64_t bd = ((DW & ~0xFFFFFFFFull) | bx) + (slot_off(e) >> 4);
                const uint32_t* hh = e < 2 ? h2a + 16 * e : h2b + 16 * (e - 2);
                WG_FENCE();
#pragma unroll
                for (int k = 0; k < (e < 3 ? 4 : 2); k++) wgmma_rl_112(ac, hh[4 * k], hh[4 * k + 1], hh[4 * k + 2], hh[4 * k + 3], bd + (k >> 1) * 512 + (k & 1) * 16, (e | k) != 0);
                WG_COMMIT();
                if (e > 0) { WG_WAIT(1); warp_arrive(BAR(B_EMPTY + e - 1)); }
            }
            PROFC(22);
            uint32_t ad = mkdesc(sb + 4 * 16384 + 8192 + w * 1024, DAN), bd = bx + 4 * 1024, fb_ = BAR(B_FULL + 4), eb_ = BAR(B_EMPTY + 3), par = sc;
#pragma unroll 1
            for (int e = 4; e < 25; e++) {
                mbar_wait_c(fb_, par);
                WG_FENCE();
                wgmma_ss_112<DAN, DW>(ac, ad, bd, 1);
                wgmma_ss_112<DAN, DW>(ac, ad + 256, bd + 16, 1);
                WG_COMMIT();
                WG_WAIT(1);
                warp_arrive(eb_);
                eb_ = fb_ + 8 * (B_EMPTY - B_FULL);
                ad += 1024; bd += 1024; fb_ += 8;
                if (e == 11 || e == 23) { ad -= 12 * 1024; bd -= 12 * 1024; fb_ -= 96; par = (par ^ 1) | sc; }
            }
            mbar_wait_cluster(BAR(B_PEER), sc);
            WG_WAIT(0);
            reg_fence<56>(ac);
            PROFC(24);
            uint32_t rdst, rbar;
            asm volatile("mapa.shared::cluster.u32 %0, %1, %2;" : "=r"(rdst) : "r"(sb + OFF_Y + (5 + w) * 16384 + t * 16), "r"(kh ^ 1 ^ sc));
            asm volatile("mapa.shared::cluster.u32 %0, %1, %2;" : "=r"(rbar) : "r"(BAR(B_XCH + w)), "r"(kh ^ 1 ^ sc));
#pragma unroll
            for (int g = 0; g < 7; g++) {
                const float v0 = ac[28 + 4 * g + 0], v1 = ac[28 + 4 * g + 1];
                const float v2 = ac[28 + 4 * g + 2], v3 = ac[28 + 4 * g + 3];
                if (!sc) asm volatile("st.async.shared::cluster.mbarrier::complete_tx::bytes.v4.f32 [%0], {%1,%2,%3,%4}, [%5];"
                             ::"r"(rdst + g * 2048), "f"(v0), "f"(v1), "f"(v2), "f"(v3), "r"(rbar) : "memory");
            }
            mbar_wait_cluster(BAR(B_XCH + w), sc);
            PROFC(25);
            uint32_t op[16];
#pragma unroll
            for (int g = 0; g < 7; g++) {
                const uint4 rv = *(const uint4*)(smem + OFF_Y + (5 + w) * 16384 + t * 16 + g * 2048);
                const float2 gb = *(const float2*)(smem + M_G + 224 + (8 * g + 2 * q) * 4);
                const float v0 = ac[4 * g + 0] + __uint_as_float(rv.x), v1 = ac[4 * g + 1] + __uint_as_float(rv.y);
                const float v2 = ac[4 * g + 2] + __uint_as_float(rv.z), v3 = ac[4 * g + 3] + __uint_as_float(rv.w);
                op[2 * g] = pack2(fmaf(gb.x, v0, bf_lo(x1p[2 * g])), fmaf(gb.y, v1, bf_hi(x1p[2 * g])));
                op[2 * g + 1] = pack2(fmaf(gb.x, v2, bf_lo(x1p[2 * g + 1])), fmaf(gb.y, v3, bf_hi(x1p[2 * g + 1])));
            }
            WAIT(B_EMPTY + 1, 0);
            const uint32_t oc = sb + OUT_STAGE + warp * 1792;
            const uint32_t oa = oc + (((lane >> 3) & 1) * 8 + (lane & 7)) * 112 + (lane >> 4) * 16;
            stsm4(oa, op[0], op[1], op[2], op[3]); stsm4(oa + 32, op[4], op[5], op[6], op[7]); stsm4(oa + 64, op[8], op[9], op[10], op[11]);
            asm volatile("stmatrix.sync.aligned.m8n8.x2.shared.b16 [%0], {%1,%2};" ::"r"(oa + 96), "r"(op[12]), "r"(op[13]));
            fence_async_smem();
            __syncwarp();
            asm volatile("{\n.reg .pred p;\nelect.sync _|p, 0xffffffff;\n@p cp.async.bulk.tensor.3d.global.shared::cta.bulk_group [%0, {%2, %3, %4}], [%1];\n"
                         "cp.async.bulk.commit_group;\ncp.async.bulk.wait_group.read 0;\n}" ::"l"(&p.om), "r"(oc), "r"(56 * j), "r"(128 * r + 16 * warp), "r"(0) : "memory");
        }
        PROFC(26);
        bar_sync(1 + w, 128);
        if (wi == 0) warp_arrive(BAR(B_DONE));
        return;
    }
    helper_late(p, r, j, warp PROF_ARGS);
}

#undef act
typedef CUresult (*EncodeFn)(CUtensorMap*, CUtensorMapDataType, cuuint32_t, void*, const cuuint64_t*, const cuuint64_t*, const cuuint32_t*,
                             const cuuint32_t*, CUtensorMapInterleave, CUtensorMapSwizzle, CUtensorMapL2promotion, CUtensorMapFloatOOBfill);

static void make_map(EncodeFn fn, CUtensorMap* m, const void* ptr, uint64_t d0, uint64_t d1, uint64_t d2, uint64_t s1, uint64_t s2,
                     uint32_t b0, uint32_t b1, uint32_t b2, CUtensorMapSwizzle sw) {
    cuuint64_t dims[3] = {d0, d1, d2}, strides[2] = {s1, s2};
    cuuint32_t box[3] = {b0, b1, b2}, es[3] = {1, 1, 1};
    CUresult rc = fn(m, CU_TENSOR_MAP_DATA_TYPE_BFLOAT16, 3, (void*)ptr, dims, strides, box, es, CU_TENSOR_MAP_INTERLEAVE_NONE, sw,
                     CU_TENSOR_MAP_L2_PROMOTION_L2_128B, CU_TENSOR_MAP_FLOAT_OOB_FILL_NONE);
    (void)rc;
}

extern "C" void kernel_launch(void* const* d_in, const int* in_sizes, int n_in, void* d_out, int out_size) {
    (void)in_sizes; (void)n_in; (void)out_size;
    static EncodeFn fn = nullptr;
    static uint32_t* act_base = nullptr;
    if (!fn) {
        cudaDriverEntryPointQueryResult st;
        cudaGetDriverEntryPoint("cuTensorMapEncodeTiled", (void**)&fn, cudaEnableDefault, &st);
        void* a = nullptr;
        cudaGetSymbolAddress(&a, g_act);
        act_base = (uint32_t*)(((uintptr_t)a + 0xFFFFF) & ~(uintptr_t)0xFFFFF);
        cudaFuncSetAttribute(fused_block_kernel, cudaFuncAttributeMaxDynamicSharedMemorySize, SMEM_BYTES);
    }
    Params p;
    p.x = (const bf16*)d_in[0];
    const bf16* wqkv = (const bf16*)d_in[1];
    p.wqkv = wqkv;
    p.wop = (const bf16*)d_in[2];
    p.wg = (const bf16*)d_in[4];
    p.wu = (const bf16*)d_in[5];
    p.wd = (const bf16*)d_in[6];
    p.c = (const bf16*)d_in[7];
    p.wmod = (const bf16*)d_in[8];
    p.out = (bf16*)d_out;
    p.zero = 0;
    p.actb = act_base;
    make_map(fn, &p.wm, p.wmod, 2688, 448, 1, 5376, 5376 * 448, 16, 224, 1, CU_TENSOR_MAP_SWIZZLE_NONE);
    make_map(fn, &p.wm2, p.wmod, 2688, 448, 1, 5376, 5376 * 448, 32, 224, 1, CU_TENSOR_MAP_SWIZZLE_NONE);
    make_map(fn, &p.om, p.out, 448, 2048, 1, 896, 896 * 2048, 56, 16, 1, CU_TENSOR_MAP_SWIZZLE_NONE);
    make_map(fn, &p.xm, p.x, 448, 2048, 1, 896, 896 * 2048, 64, 128, 1, CU_TENSOR_MAP_SWIZZLE_128B);
    make_map(fn, &p.qkv, wqkv, 1344, 448, 1, 2688, 2688 * 448, 64, 224, 1, CU_TENSOR_MAP_SWIZZLE_128B);
    make_map(fn, &p.wo, p.wop, 448, 448, 1, 896, 896 * 448, 64, 224, 1, CU_TENSOR_MAP_SWIZZLE_128B);
    make_map(fn, &p.ga, p.wg, 64, 448, 28, 3584, 128, 64, 32, 2, CU_TENSOR_MAP_SWIZZLE_128B);
    make_map(fn, &p.ua, p.wu, 64, 448, 28, 3584, 128, 64, 32, 2, CU_TENSOR_MAP_SWIZZLE_128B);
    make_map(fn, &p.gb, p.wg, 64, 448, 28, 3584, 128, 64, 64, 1, CU_TENSOR_MAP_SWIZZLE_128B);
    make_map(fn, &p.ub, p.wu, 64, 448, 28, 3584, 128, 64, 64, 1, CU_TENSOR_MAP_SWIZZLE_128B);
    make_map(fn, &p.gc, p.wg, 32, 448, 56, 3584, 64, 32, 64, 1, CU_TENSOR_MAP_SWIZZLE_64B);
    make_map(fn, &p.uc, p.wu, 32, 448, 56, 3584, 64, 32, 64, 1, CU_TENSOR_MAP_SWIZZLE_64B);
    make_map(fn, &p.dn, p.wd, 8, 1792, 56, 896, 16, 8, 32, 7, CU_TENSOR_MAP_SWIZZLE_NONE);
    fused_block_kernel<<<GRID, 384, SMEM_BYTES>>>(p);
}
```

```cpp
#include <cuda_runtime.h>
#include <cuda_bf16.h>
#include <cuda.h>
#include <stdint.h>

typedef __nv_bfloat16 bf16;

template<uint64_t CA, uint64_t CB> __device__ __forceinline__ void wgmma_sk_160(float* d, uint32_t da, uint32_t db, int sd) {
  asm volatile("{\n.reg .pred p;\n.reg .b64 a, b;\nsetp.ne.b32 p, %82, 0;\nmov.b64 a, {%80, %83};\nmov.b64 b, {%81, %84};\n"
    "wgmma.mma_async.sync.aligned.m64n160k16.f32.bf16.bf16 {%0,%1,%2,%3,%4,%5,%6,%7,%8,%9,%10,%11,%12,%13,%14,%15,%16,%17,%18,%19,%20,%21,%22,%23,%24,%25,%26,%27,%28,%29,%30,%31,%32,%33,%34,%35,%36,%37,%38,%39,%40,%41,%42,%43,%44,%45,%46,%47,%48,%49,%50,%51,%52,%53,%54,%55,%56,%57,%58,%59,%60,%61,%62,%63,%64,%65,%66,%67,%68,%69,%70,%71,%72,%73,%74,%75,%76,%77,%78,%79}, a, b, p, 1, 1, 0, 0;\n}\n"
    : "+f"(d[0]),"+f"(d[1]),"+f"(d[2]),"+f"(d[3]),"+f"(d[4]),"+f"(d[5]),"+f"(d[6]),"+f"(d[7]),"+f"(d[8]),"+f"(d[9]),"+f"(d[10]),"+f"(d[11]),"+f"(d[12]),"+f"(d[13]),"+f"(d[14]),"+f"(d[15]),"+f"(d[16]),"+f"(d[17]),"+f"(d[18]),"+f"(d[19]),"+f"(d[20]),"+f"(d[21]),"+f"(d[22]),"+f"(d[23]),"+f"(d[24]),"+f"(d[25]),"+f"(d[26]),"+f"(d[27]),"+f"(d[28]),"+f"(d[29]),"+f"(d[30]),"+f"(d[31]),"+f"(d[32]),"+f"(d[33]),"+f"(d[34]),"+f"(d[35]),"+f"(d[36]),"+f"(d[37]),"+f"(d[38]),"+f"(d[39]),"+f"(d[40]),"+f"(d[41]),"+f"(d[42]),"+f"(d[43]),"+f"(d[44]),"+f"(d[45]),"+f"(d[46]),"+f"(d[47]),"+f"(d[48]),"+f"(d[49]),"+f"(d[50]),"+f"(d[51]),"+f"(d[52]),"+f"(d[53]),"+f"(d[54]),"+f"(d[55]),"+f"(d[56]),"+f"(d[57]),"+f"(d[58]),"+f"(d[59]),"+f"(d[60]),"+f"(d[61]),"+f"(d[62]),"+f"(d[63]),"+f"(d[64]),"+f"(d[65]),"+f"(d[66]),"+f"(d[67]),"+f"(d[68]),"+f"(d[69]),"+f"(d[70]),"+f"(d[71]),"+f"(d[72]),"+f"(d[73]),"+f"(d[74]),"+f"(d[75]),"+f"(d[76]),"+f"(d[77]),"+f"(d[78]),"+f"(d[79])
    : "r"(da), "r"(db), "r"(sd), "n"((uint32_t)(CA >> 32)), "n"((uint32_t)(CB >> 32)));
}
__device__ __forceinline__ void wgmma_rl_56(float* d, uint32_t a0, uint32_t a1, uint32_t a2, uint32_t a3, uint64_t db, int sd) {
  asm volatile("{\n.reg .pred p;\nsetp.ne.b32 p, %33, 0;\n"
    "wgmma.mma_async.sync.aligned.m64n56k16.f32.bf16.bf16 {%0,%1,%2,%3,%4,%5,%6,%7,%8,%9,%10,%11,%12,%13,%14,%15,%16,%17,%18,%19,%20,%21,%22,%23,%24,%25,%26,%27}, {%28,%29,%30,%31}, %32, p, 1, 1, 1;\n}\n"
    : "+f"(d[0]),"+f"(d[1]),"+f"(d[2]),"+f"(d[3]),"+f"(d[4]),"+f"(d[5]),"+f"(d[6]),"+f"(d[7]),"+f"(d[8]),"+f"(d[9]),"+f"(d[10]),"+f"(d[11]),"+f"(d[12]),"+f"(d[13]),"+f"(d[14]),"+f"(d[15]),"+f"(d[16]),"+f"(d[17]),"+f"(d[18]),"+f"(d[19]),"+f"(d[20]),"+f"(d[21]),"+f"(d[22]),"+f"(d[23]),"+f"(d[24]),"+f"(d[25]),"+f"(d[26]),"+f"(d[27])
    : "r"(a0), "r"(a1), "r"(a2), "r"(a3), "l"(db), "r"(sd));
}
template<uint64_t CA, uint64_t CB> __device__ __forceinline__ void wgmma_ss_56(float* d, uint32_t da, uint32_t db, int sd) {
  asm volatile("{\n.reg .pred p;\n.reg .b64 a, b;\nsetp.ne.b32 p, %30, 0;\nmov.b64 a, {%28, %31};\nmov.b64 b, {%29, %32};\n"
    "wgmma.mma_async.sync.aligned.m64n56k16.f32.bf16.bf16 {%0,%1,%2,%3,%4,%5,%6,%7,%8,%9,%10,%11,%12,%13,%14,%15,%16,%17,%18,%19,%20,%21,%22,%23,%24,%25,%26,%27}, a, b, p, 1, 1, 0, 1;\n}\n"
    : "+f"(d[0]),"+f"(d[1]),"+f"(d[2]),"+f"(d[3]),"+f"(d[4]),"+f"(d[5]),"+f"(d[6]),"+f"(d[7]),"+f"(d[8]),"+f"(d[9]),"+f"(d[10]),"+f"(d[11]),"+f"(d[12]),"+f"(d[13]),"+f"(d[14]),"+f"(d[15]),"+f"(d[16]),"+f"(d[17]),"+f"(d[18]),"+f"(d[19]),"+f"(d[20]),"+f"(d[21]),"+f"(d[22]),"+f"(d[23]),"+f"(d[24]),"+f"(d[25]),"+f"(d[26]),"+f"(d[27])
    : "r"(da), "r"(db), "r"(sd), "n"((uint32_t)(CA >> 32)), "n"((uint32_t)(CB >> 32)));
}
__device__ __forceinline__ void wgmma_rl_256(float* d, uint32_t a0, uint32_t a1, uint32_t a2, uint32_t a3, uint64_t db, int sd) {
  asm volatile("{\n.reg .pred p;\nsetp.ne.b32 p, %133, 0;\n"
    "wgmma.mma_async.sync.aligned.m64n256k16.f32.bf16.bf16 {%0,%1,%2,%3,%4,%5,%6,%7,%8,%9,%10,%11,%12,%13,%14,%15,%16,%17,%18,%19,%20,%21,%22,%23,%24,%25,%26,%27,%28,%29,%30,%31,%32,%33,%34,%35,%36,%37,%38,%39,%40,%41,%42,%43,%44,%45,%46,%47,%48,%49,%50,%51,%52,%53,%54,%55,%56,%57,%58,%59,%60,%61,%62,%63,%64,%65,%66,%67,%68,%69,%70,%71,%72,%73,%74,%75,%76,%77,%78,%79,%80,%81,%82,%83,%84,%85,%86,%87,%88,%89,%90,%91,%92,%93,%94,%95,%96,%97,%98,%99,%100,%101,%102,%103,%104,%105,%106,%107,%108,%109,%110,%111,%112,%113,%114,%115,%116,%117,%118,%119,%120,%121,%122,%123,%124,%125,%126,%127}, {%128,%129,%130,%131}, %132, p, 1, 1, 1;\n}\n"
    : "+f"(d[0]),"+f"(d[1]),"+f"(d[2]),"+f"(d[3]),"+f"(d[4]),"+f"(d[5]),"+f"(d[6]),"+f"(d[7]),"+f"(d[8]),"+f"(d[9]),"+f"(d[10]),"+f"(d[11]),"+f"(d[12]),"+f"(d[13]),"+f"(d[14]),"+f"(d[15]),"+f"(d[16]),"+f"(d[17]),"+f"(d[18]),"+f"(d[19]),"+f"(d[20]),"+f"(d[21]),"+f"(d[22]),"+f"(d[23]),"+f"(d[24]),"+f"(d[25]),"+f"(d[26]),"+f"(d[27]),"+f"(d[28]),"+f"(d[29]),"+f"(d[30]),"+f"(d[31]),"+f"(d[32]),"+f"(d[33]),"+f"(d[34]),"+f"(d[35]),"+f"(d[36]),"+f"(d[37]),"+f"(d[38]),"+f"(d[39]),"+f"(d[40]),"+f"(d[41]),"+f"(d[42]),"+f"(d[43]),"+f"(d[44]),"+f"(d[45]),"+f"(d[46]),"+f"(d[47]),"+f"(d[48]),"+f"(d[49]),"+f"(d[50]),"+f"(d[51]),"+f"(d[52]),"+f"(d[53]),"+f"(d[54]),"+f"(d[55]),"+f"(d[56]),"+f"(d[57]),"+f"(d[58]),"+f"(d[59]),"+f"(d[60]),"+f"(d[61]),"+f"(d[62]),"+f"(d[63]),"+f"(d[64]),"+f"(d[65]),"+f"(d[66]),"+f"(d[67]),"+f"(d[68]),"+f"(d[69]),"+f"(d[70]),"+f"(d[71]),"+f"(d[72]),"+f"(d[73]),"+f"(d[74]),"+f"(d[75]),"+f"(d[76]),"+f"(d[77]),"+f"(d[78]),"+f"(d[79]),"+f"(d[80]),"+f"(d[81]),"+f"(d[82]),"+f"(d[83]),"+f"(d[84]),"+f"(d[85]),"+f"(d[86]),"+f"(d[87]),"+f"(d[88]),"+f"(d[89]),"+f"(d[90]),"+f"(d[91]),"+f"(d[92]),"+f"(d[93]),"+f"(d[94]),"+f"(d[95]),"+f"(d[96]),"+f"(d[97]),"+f"(d[98]),"+f"(d[99]),"+f"(d[100]),"+f"(d[101]),"+f"(d[102]),"+f"(d[103]),"+f"(d[104]),"+f"(d[105]),"+f"(d[106]),"+f"(d[107]),"+f"(d[108]),"+f"(d[109]),"+f"(d[110]),"+f"(d[111]),"+f"(d[112]),"+f"(d[113]),"+f"(d[114]),"+f"(d[115]),"+f"(d[116]),"+f"(d[117]),"+f"(d[118]),"+f"(d[119]),"+f"(d[120]),"+f"(d[121]),"+f"(d[122]),"+f"(d[123]),"+f"(d[124]),"+f"(d[125]),"+f"(d[126]),"+f"(d[127])
    : "r"(a0), "r"(a1), "r"(a2), "r"(a3), "l"(db), "r"(sd));
}
template<uint64_t CA, uint64_t CB> __device__ __forceinline__ void wgmma_ss_128(float* d, uint32_t da, uint32_t db, int sd) {
  asm volatile("{\n.reg .pred p;\n.reg .b64 a, b;\nsetp.ne.b32 p, %66, 0;\nmov.b64 a, {%64, %67};\nmov.b64 b, {%65, %68};\n"
    "wgmma.mma_async.sync.aligned.m64n128k16.f32.bf16.bf16 {%0,%1,%2,%3,%4,%5,%6,%7,%8,%9,%10,%11,%12,%13,%14,%15,%16,%17,%18,%19,%20,%21,%22,%23,%24,%25,%26,%27,%28,%29,%30,%31,%32,%33,%34,%35,%36,%37,%38,%39,%40,%41,%42,%43,%44,%45,%46,%47,%48,%49,%50,%51,%52,%53,%54,%55,%56,%57,%58,%59,%60,%61,%62,%63}, a, b, p, 1, 1, 0, 1;\n}\n"
    : "+f"(d[0]),"+f"(d[1]),"+f"(d[2]),"+f"(d[3]),"+f"(d[4]),"+f"(d[5]),"+f"(d[6]),"+f"(d[7]),"+f"(d[8]),"+f"(d[9]),"+f"(d[10]),"+f"(d[11]),"+f"(d[12]),"+f"(d[13]),"+f"(d[14]),"+f"(d[15]),"+f"(d[16]),"+f"(d[17]),"+f"(d[18]),"+f"(d[19]),"+f"(d[20]),"+f"(d[21]),"+f"(d[22]),"+f"(d[23]),"+f"(d[24]),"+f"(d[25]),"+f"(d[26]),"+f"(d[27]),"+f"(d[28]),"+f"(d[29]),"+f"(d[30]),"+f"(d[31]),"+f"(d[32]),"+f"(d[33]),"+f"(d[34]),"+f"(d[35]),"+f"(d[36]),"+f"(d[37]),"+f"(d[38]),"+f"(d[39]),"+f"(d[40]),"+f"(d[41]),"+f"(d[42]),"+f"(d[43]),"+f"(d[44]),"+f"(d[45]),"+f"(d[46]),"+f"(d[47]),"+f"(d[48]),"+f"(d[49]),"+f"(d[50]),"+f"(d[51]),"+f"(d[52]),"+f"(d[53]),"+f"(d[54]),"+f"(d[55]),"+f"(d[56]),"+f"(d[57]),"+f"(d[58]),"+f"(d[59]),"+f"(d[60]),"+f"(d[61]),"+f"(d[62]),"+f"(d[63])
    : "r"(da), "r"(db), "r"(sd), "n"((uint32_t)(CA >> 32)), "n"((uint32_t)(CB >> 32)));
}
template<uint64_t CA, uint64_t CB> __device__ __forceinline__ void wgmma_ss_64(float* d, uint32_t da, uint32_t db, int sd) {
  asm volatile("{\n.reg .pred p;\n.reg .b64 a, b;\nsetp.ne.b32 p, %34, 0;\nmov.b64 a, {%32, %35};\nmov.b64 b, {%33, %36};\n"
    "wgmma.mma_async.sync.aligned.m64n64k16.f32.bf16.bf16 {%0,%1,%2,%3,%4,%5,%6,%7,%8,%9,%10,%11,%12,%13,%14,%15,%16,%17,%18,%19,%20,%21,%22,%23,%24,%25,%26,%27,%28,%29,%30,%31}, a, b, p, 1, 1, 0, 1;\n}\n"
    : "+f"(d[0]),"+f"(d[1]),"+f"(d[2]),"+f"(d[3]),"+f"(d[4]),"+f"(d[5]),"+f"(d[6]),"+f"(d[7]),"+f"(d[8]),"+f"(d[9]),"+f"(d[10]),"+f"(d[11]),"+f"(d[12]),"+f"(d[13]),"+f"(d[14]),"+f"(d[15]),"+f"(d[16]),"+f"(d[17]),"+f"(d[18]),"+f"(d[19]),"+f"(d[20]),"+f"(d[21]),"+f"(d[22]),"+f"(d[23]),"+f"(d[24]),"+f"(d[25]),"+f"(d[26]),"+f"(d[27]),"+f"(d[28]),"+f"(d[29]),"+f"(d[30]),"+f"(d[31])
    : "r"(da), "r"(db), "r"(sd), "n"((uint32_t)(CA >> 32)), "n"((uint32_t)(CB >> 32)));
}
template<uint64_t CA, uint64_t CB> __device__ __forceinline__ void wgmma_ss_112(float* d, uint32_t da, uint32_t db, int sd) {
  asm volatile("{\n.reg .pred p;\n.reg .b64 a, b;\nsetp.ne.b32 p, %58, 0;\nmov.b64 a, {%56, %59};\nmov.b64 b, {%57, %60};\n"
    "wgmma.mma_async.sync.aligned.m64n112k16.f32.bf16.bf16 {%0,%1,%2,%3,%4,%5,%6,%7,%8,%9,%10,%11,%12,%13,%14,%15,%16,%17,%18,%19,%20,%21,%22,%23,%24,%25,%26,%27,%28,%29,%30,%31,%32,%33,%34,%35,%36,%37,%38,%39,%40,%41,%42,%43,%44,%45,%46,%47,%48,%49,%50,%51,%52,%53,%54,%55}, a, b, p, 1, 1, 0, 1;\n}\n"
    : "+f"(d[0]),"+f"(d[1]),"+f"(d[2]),"+f"(d[3]),"+f"(d[4]),"+f"(d[5]),"+f"(d[6]),"+f"(d[7]),"+f"(d[8]),"+f"(d[9]),"+f"(d[10]),"+f"(d[11]),"+f"(d[12]),"+f"(d[13]),"+f"(d[14]),"+f"(d[15]),"+f"(d[16]),"+f"(d[17]),"+f"(d[18]),"+f"(d[19]),"+f"(d[20]),"+f"(d[21]),"+f"(d[22]),"+f"(d[23]),"+f"(d[24]),"+f"(d[25]),"+f"(d[26]),"+f"(d[27]),"+f"(d[28]),"+f"(d[29]),"+f"(d[30]),"+f"(d[31]),"+f"(d[32]),"+f"(d[33]),"+f"(d[34]),"+f"(d[35]),"+f"(d[36]),"+f"(d[37]),"+f"(d[38]),"+f"(d[39]),"+f"(d[40]),"+f"(d[41]),"+f"(d[42]),"+f"(d[43]),"+f"(d[44]),"+f"(d[45]),"+f"(d[46]),"+f"(d[47]),"+f"(d[48]),"+f"(d[49]),"+f"(d[50]),"+f"(d[51]),"+f"(d[52]),"+f"(d[53]),"+f"(d[54]),"+f"(d[55])
    : "r"(da), "r"(db), "r"(sd), "n"((uint32_t)(CA >> 32)), "n"((uint32_t)(CB >> 32)));
}
__device__ __forceinline__ void wgmma_rl_112(float* d, uint32_t a0, uint32_t a1, uint32_t a2, uint32_t a3, uint64_t db, int sd) {
  asm volatile("{\n.reg .pred p;\nsetp.ne.b32 p, %61, 0;\n"
    "wgmma.mma_async.sync.aligned.m64n112k16.f32.bf16.bf16 {%0,%1,%2,%3,%4,%5,%6,%7,%8,%9,%10,%11,%12,%13,%14,%15,%16,%17,%18,%19,%20,%21,%22,%23,%24,%25,%26,%27,%28,%29,%30,%31,%32,%33,%34,%35,%36,%37,%38,%39,%40,%41,%42,%43,%44,%45,%46,%47,%48,%49,%50,%51,%52,%53,%54,%55}, {%56,%57,%58,%59}, %60, p, 1, 1, 1;\n}\n"
    : "+f"(d[0]),"+f"(d[1]),"+f"(d[2]),"+f"(d[3]),"+f"(d[4]),"+f"(d[5]),"+f"(d[6]),"+f"(d[7]),"+f"(d[8]),"+f"(d[9]),"+f"(d[10]),"+f"(d[11]),"+f"(d[12]),"+f"(d[13]),"+f"(d[14]),"+f"(d[15]),"+f"(d[16]),"+f"(d[17]),"+f"(d[18]),"+f"(d[19]),"+f"(d[20]),"+f"(d[21]),"+f"(d[22]),"+f"(d[23]),"+f"(d[24]),"+f"(d[25]),"+f"(d[26]),"+f"(d[27]),"+f"(d[28]),"+f"(d[29]),"+f"(d[30]),"+f"(d[31]),"+f"(d[32]),"+f"(d[33]),"+f"(d[34]),"+f"(d[35]),"+f"(d[36]),"+f"(d[37]),"+f"(d[38]),"+f"(d[39]),"+f"(d[40]),"+f"(d[41]),"+f"(d[42]),"+f"(d[43]),"+f"(d[44]),"+f"(d[45]),"+f"(d[46]),"+f"(d[47]),"+f"(d[48]),"+f"(d[49]),"+f"(d[50]),"+f"(d[51]),"+f"(d[52]),"+f"(d[53]),"+f"(d[54]),"+f"(d[55])
    : "r"(a0), "r"(a1), "r"(a2), "r"(a3), "l"(db), "r"(sd));
}

constexpr int DM = 448;
constexpr int NCTA = 128;
#define MAPPING 1
#define GRID 128
#define PINGPONG 0
#define WIN 6
#define WIN_END 25
#define UNR_B 1
#define UNR_C 1
constexpr int kB = UNR_B, kC = UNR_C;
#define LIKELY(x) __builtin_expect(!!(x), 1)
#define PACE 1
#define PACE_END 6
#define GEMV_AT 0
#define NPRE 14
#define ATT_OFF 0
#define ATT_WG 1
#define XFIRST 7
#define KDELAY 0
#define KEARLY 1
#define VPRE 3
#define VGATE 2
#define LNMODE 1
#define MAP_S 4
constexpr int SPIN_LIMIT = 1 << 22;

constexpr uint32_t OFF_X = 0, OFF_Y = 114688, OFF_MISC = 229376, SMEM_BYTES = 232448;
constexpr uint32_t Y_VR = 0, Y_K = 28672, Y_KOWN = 57344, Y_VOWN = 71680, Y_Q = 86016;
constexpr uint32_t HALF = 57344;
constexpr uint32_t X_STAT = 49152;
constexpr uint32_t OUT_STAGE = 16384;
constexpr uint32_t M_BAR = OFF_MISC;
constexpr uint32_t M_ST = OFF_MISC + 512;
constexpr uint32_t M_G = OFF_MISC + 2304;
constexpr uint32_t M_EPOCH = OFF_MISC + 3040;
enum { B_XFULL = 0, B_FULLK = 7, B_FULLV = 8, B_FULLQ, B_KRFULL, B_VRFULL, B_WOFULL, B_XCH, B_MOD1 = 15, B_FULL = 16, B_WMFULL = 30,
       B_EMPTY = 32, B_XFREE = B_EMPTY + 12, B_GEMV, B_PEER,
       B_PUB = 47,
       B_WMFREE = 56, B_HRDY, B_GFULL = B_HRDY + 3, B_DONE = 31, B_DUMMY = B_GEMV };

__device__ uint32_t g_ticket;
__device__ __align__(128) uint32_t g_mod[8 * 6 * DM];
__device__ __align__(128) uint32_t g_flag[144 * 128];
constexpr int RB_WORDS = 262144, RB_KV = 0, RB_O = 57344, RB_X1 = 86016, RB_H2 = 143360, RB_ST = 258048;
__device__ __align__(128) uint32_t g_act[18 * RB_WORDS];
__device__ __align__(128) uint32_t g_wd[56 * 4 * 1792];
#define PROFH(id)
#define PROFH1(id)
#define PROFC(id)

struct alignas(64) Params {
    CUtensorMap wm, wm2, om, xm, qkv, wo, ga, ua, gb, ub, gc, uc, dn;
    const bf16 *x, *c, *wqkv, *wmod, *wg, *wu, *wd, *wop;
    bf16* out;
    uint32_t* actb;
    uint32_t zero;
};

__device__ __forceinline__ void mbar_init(uint32_t bar, int cnt) { asm volatile("mbarrier.init.shared::cta.b64 [%0], %1;" ::"r"(bar), "r"(cnt) : "memory"); }
__device__ __forceinline__ void mbar_expect_tx(uint32_t bar, uint32_t bytes) { asm volatile("mbarrier.arrive.expect_tx.shared::cta.b64 _, [%0], %1;" ::"r"(bar), "r"(bytes) : "memory"); }
__device__ __forceinline__ void mbar_arrive(uint32_t bar) { asm volatile("mbarrier.arrive.shared::cta.b64 _, [%0];" ::"r"(bar) : "memory"); }
__device__ __forceinline__ void mbar_wait(uint32_t bar, uint32_t parity) {
    uint32_t ok; int n = 0;
    do {
        asm volatile("{\n.reg .pred p;\nmbarrier.try_wait.parity.shared::cta.b64 p, [%1], %2;\nselp.u32 %0, 1, 0, p;\n}" : "=r"(ok) : "r"(bar), "r"(parity) : "memory");
        if (++n > SPIN_LIMIT) __trap();
    } while (!ok);
}
__device__ __forceinline__ void mbar_wait_c(uint32_t bar, uint32_t parity) {
    asm volatile("{\n.reg .pred p;\nWL:\nmbarrier.try_wait.parity.shared::cta.b64 p, [%0], %1, 0x989680;\n@!p bra WL;\n}" ::"r"(bar), "r"(parity) : "memory");
}
__device__ __forceinline__ void mbar_wait_cluster(uint32_t bar, uint32_t parity) {
    asm volatile("{\n.reg .pred p;\nWL:\nmbarrier.try_wait.parity.acquire.cluster.shared::cta.b64 p, [%0], %1, 0x989680;\n@!p bra WL;\n}" ::"r"(bar), "r"(parity) : "memory");
}
__device__ __forceinline__ void warp_arrive(uint32_t bar) {
    __syncwarp();
    asm volatile("{\n.reg .pred p;\nelect.sync _|p, 0xffffffff;\n@p mbarrier.arrive.shared::cta.b64 _, [%0];\n}" ::"r"(bar) : "memory");
}
__device__ __forceinline__ int opaque(int v) { return __shfl_sync(~0u, v, 0); }
__device__ __forceinline__ int fresh_tid() { int v; asm volatile("mov.u32 %0, %%tid.x;" : "=r"(v)); return v; }
__device__ __forceinline__ void bar_sync(int id, int n) { asm volatile("bar.sync %0, %1;" ::"r"(id), "r"(n) : "memory"); }
__device__ __forceinline__ void bar_arrive(int id, int n) { asm volatile("bar.arrive %0, %1;" ::"r"(id), "r"(n) : "memory"); }
__device__ __forceinline__ void fence_async_smem() { asm volatile("fence.proxy.async.shared::cta;" ::: "memory"); }
__device__ __forceinline__ void fence_async_global() { asm volatile("fence.proxy.async.global;" ::: "memory"); }
__device__ __forceinline__ void fence_gpu() { asm volatile("fence.release.gpu;" ::: "memory"); }
__device__ __forceinline__ void tma3(uint32_t dst, const CUtensorMap* m, int c0, int c1, int c2, uint32_t bar) {
    asm volatile("cp.async.bulk.tensor.3d.shared::cluster.global.mbarrier::complete_tx::bytes [%0], [%1, {%3, %4, %5}], [%2];"
                 ::"r"(dst), "l"(m), "r"(bar), "r"(c0), "r"(c1), "r"(c2) : "memory");
}
__device__ __forceinline__ void bulk_load(uint32_t dst, const void* src, uint32_t bytes, uint32_t bar) {
    asm volatile("cp.async.bulk.shared::cluster.global.mbarrier::complete_tx::bytes [%0], [%1], %2, [%3];" ::"r"(dst), "l"(src), "r"(bytes), "r"(bar) : "memory");
}
__device__ __forceinline__ void expect_e(uint32_t bar, uint32_t bytes) {
    asm volatile("{\n.reg .pred p;\nelect.sync _|p, 0xffffffff;\n@p mbarrier.arrive.expect_tx.shared::cta.b64 _, [%0], %1;\n}" ::"r"(bar), "r"(bytes) : "memory");
}
__device__ __forceinline__ void tma3_e(uint32_t dst, const CUtensorMap* m, int c0, int c1, int c2, uint32_t bar) {
    asm volatile("{\n.reg .pred p;\nelect.sync _|p, 0xffffffff;\n@p cp.async.bulk.tensor.3d.shared::cluster.global.mbarrier::complete_tx::bytes [%0], [%1, {%3, %4, %5}], [%2];\n}"
                 ::"r"(dst), "l"(m), "r"(bar), "r"(c0), "r"(c1), "r"(c2) : "memory");
}
__device__ __forceinline__ void bulk_e(uint32_t dst, const void* src, uint32_t bytes, uint32_t bar) {
    asm volatile("{\n.reg .pred p;\nelect.sync _|p, 0xffffffff;\n@p cp.async.bulk.shared::cluster.global.mbarrier::complete_tx::bytes [%0], [%1], %2, [%3];\n}"
                 ::"r"(dst), "l"(src), "r"(bytes), "r"(bar) : "memory");
}
__device__ __forceinline__ void init_e(uint32_t bar, int cnt) {
    asm volatile("{\n.reg .pred p;\nelect.sync _|p, 0xffffffff;\n@p mbarrier.init.shared::cta.b64 [%0], %1;\n}" ::"r"(bar), "r"(cnt) : "memory");
}
__device__ __forceinline__ void l2_prefetch_e(const void* src, uint32_t bytes) {
    asm volatile("{\n.reg .pred p;\nelect.sync _|p, 0xffffffff;\n@p cp.async.bulk.prefetch.L2.global [%0], %1;\n}" ::"l"(src), "r"(bytes) : "memory");
}
__device__ __forceinline__ uint32_t ld_relaxed(const uint32_t* p) { uint32_t v; asm volatile("ld.relaxed.gpu.global.u32 %0, [%1];" : "=r"(v) : "l"(p) : "memory"); return v; }
__device__ __forceinline__ void st_relaxed(uint32_t* p, uint32_t v) { asm volatile("st.relaxed.gpu.global.u32 [%0], %1;" ::"l"(p), "r"(v) : "memory"); }
__device__ __forceinline__ uint4 ld_relaxed4(const uint4* p) { uint4 v; asm volatile("ld.relaxed.gpu.global.v4.u32 {%0,%1,%2,%3}, [%4];" : "=r"(v.x), "=r"(v.y), "=r"(v.z), "=r"(v.w) : "l"(p) : "memory"); return v; }
__device__ __forceinline__ void st_relaxed4(uint4* p, uint4 v) { asm volatile("st.relaxed.gpu.global.v4.u32 [%0], {%1,%2,%3,%4};" ::"l"(p), "r"(v.x), "r"(v.y), "r"(v.z), "r"(v.w) : "memory"); }
__device__ __forceinline__ uint4 ldg_nc4(const void* p) { uint4 v; asm volatile("ld.global.nc.L1::no_allocate.v4.u32 {%0,%1,%2,%3}, [%4];" : "=r"(v.x), "=r"(v.y), "=r"(v.z), "=r"(v.w) : "l"(p)); return v; }
__device__ __forceinline__ uint32_t ldg_nc(const void* p) { uint32_t v; asm volatile("ld.global.nc.u32 %0, [%1];" : "=r"(v) : "l"(p)); return v; }
__device__ __forceinline__ uint32_t ld_acquire(const uint32_t* p) { uint32_t v; asm volatile("ld.acquire.gpu.global.u32 %0, [%1];" : "=r"(v) : "l"(p) : "memory"); return v; }
__device__ __forceinline__ uint4 lds4(uint32_t a) { uint4 v; asm volatile("ld.shared.v4.u32 {%0,%1,%2,%3}, [%4];" : "=r"(v.x), "=r"(v.y), "=r"(v.z), "=r"(v.w) : "r"(a) : "memory"); return v; }
__device__ __forceinline__ float2 lds2f(uint32_t a) { float2 v; asm volatile("ld.shared.v2.f32 {%0,%1}, [%2];" : "=f"(v.x), "=f"(v.y) : "r"(a) : "memory"); return v; }
__device__ __forceinline__ uint32_t lds1(uint32_t a) { uint32_t v; asm volatile("ld.shared.u32 %0, [%1];" : "=r"(v) : "r"(a) : "memory"); return v; }
__device__ __forceinline__ void sts4(uint32_t a, uint4 v) { asm volatile("st.shared.v4.u32 [%0], {%1,%2,%3,%4};" ::"r"(a), "r"(v.x), "r"(v.y), "r"(v.z), "r"(v.w) : "memory"); }
__device__ __forceinline__ void sts2(uint32_t a, uint32_t x, uint32_t y) { asm volatile("st.shared.v2.u32 [%0], {%1,%2};" ::"r"(a), "r"(x), "r"(y) : "memory"); }
__device__ __forceinline__ void sts1(uint32_t a, uint32_t v) { asm volatile("st.shared.u32 [%0], %1;" ::"r"(a), "r"(v) : "memory"); }
__device__ __forceinline__ void stsm4(uint32_t a, uint32_t r0, uint32_t r1, uint32_t r2, uint32_t r3) {
    asm volatile("stmatrix.sync.aligned.m8n8.x4.shared.b16 [%0], {%1,%2,%3,%4};" ::"r"(a), "r"(r0), "r"(r1), "r"(r2), "r"(r3));
}
__device__ __forceinline__ uint32_t pack2(float lo, float hi) { uint32_t r; asm("cvt.rn.bf16x2.f32 %0, %1, %2;" : "=r"(r) : "f"(hi), "f"(lo)); return r; }
__device__ __forceinline__ uint32_t pack2_relu(float lo, float hi) { uint32_t r; asm("cvt.rn.relu.bf16x2.f32 %0, %1, %2;" : "=r"(r) : "f"(hi), "f"(lo)); return r; }
__device__ __forceinline__ uint32_t hfma2(uint32_t a, uint32_t b, uint32_t c) { uint32_t r; asm("fma.rn.bf16x2 %0, %1, %2, %3;" : "=r"(r) : "r"(a), "r"(b), "r"(c)); return r; }
__device__ __forceinline__ uint32_t hmul2(uint32_t a, uint32_t b) { uint32_t r; asm("mul.rn.bf16x2 %0, %1, %2;" : "=r"(r) : "r"(a), "r"(b)); return r; }
__device__ __forceinline__ float bf_lo(uint32_t v) { return __uint_as_float(v << 16); }
__device__ __forceinline__ float bf_hi(uint32_t v) { return __uint_as_float(v & 0xFFFF0000u); }
__device__ __forceinline__ float bf_round(float v) { return bf_lo(pack2(v, 0.f)); }
__device__ __forceinline__ float ex2(float x) { float r; asm("ex2.approx.ftz.f32 %0, %1;" : "=f"(r) : "f"(x)); return r; }
__device__ __forceinline__ void mma16816(float* d, uint32_t a0, uint32_t a1, uint32_t a2, uint32_t a3, uint32_t b0, uint32_t b1) {
    asm("mma.sync.aligned.m16n8k16.row.col.f32.bf16.bf16.f32 {%0,%1,%2,%3}, {%4,%5,%6,%7}, {%8,%9}, {%0,%1,%2,%3};"
        : "+f"(d[0]), "+f"(d[1]), "+f"(d[2]), "+f"(d[3]) : "r"(a0), "r"(a1), "r"(a2), "r"(a3), "r"(b0), "r"(b1));
}
__device__ __forceinline__ void mma16816_first(float* d, uint32_t a0, uint32_t a1, uint32_t a2, uint32_t a3, uint32_t b0, uint32_t b1) {
    asm volatile("mma.sync.aligned.m16n8k16.row.col.f32.bf16.bf16.f32 {%0,%1,%2,%3}, {%4,%5,%6,%7}, {%8,%9}, {%10,%10,%10,%10};"
        : "=f"(d[0]), "=f"(d[1]), "=f"(d[2]), "=f"(d[3]) : "r"(a0), "r"(a1), "r"(a2), "r"(a3), "r"(b0), "r"(b1), "f"(0.f));
}
__device__ __forceinline__ void mma16816_v(float* d, uint32_t a0, uint32_t a1, uint32_t a2, uint32_t a3, uint32_t b0, uint32_t b1) {
    asm volatile("mma.sync.aligned.m16n8k16.row.col.f32.bf16.bf16.f32 {%0,%1,%2,%3}, {%4,%5,%6,%7}, {%8,%9}, {%0,%1,%2,%3};"
        : "+f"(d[0]), "+f"(d[1]), "+f"(d[2]), "+f"(d[3]) : "r"(a0), "r"(a1), "r"(a2), "r"(a3), "r"(b0), "r"(b1));
}
__device__ __forceinline__ void mma1688(float* d, uint32_t a0, uint32_t a1, uint32_t b0) {
    asm("mma.sync.aligned.m16n8k8.row.col.f32.bf16.bf16.f32 {%0,%1,%2,%3}, {%4,%5}, {%6}, {%0,%1,%2,%3};"
        : "+f"(d[0]), "+f"(d[1]), "+f"(d[2]), "+f"(d[3]) : "r"(a0), "r"(a1), "r"(b0));
}
__device__ __forceinline__ void ldsm4(uint32_t a, uint32_t* r) {
    asm volatile("ldmatrix.sync.aligned.m8n8.x4.shared.b16 {%0,%1,%2,%3}, [%4];" : "=r"(r[0]), "=r"(r[1]), "=r"(r[2]), "=r"(r[3]) : "r"(a));
}
__device__ __forceinline__ void ldsm4t(uint32_t a, uint32_t* r) {
    asm volatile("ldmatrix.sync.aligned.m8n8.x4.trans.shared.b16 {%0,%1,%2,%3}, [%4];" : "=r"(r[0]), "=r"(r[1]), "=r"(r[2]), "=r"(r[3]) : "r"(a));
}
__device__ __forceinline__ uint32_t nz(uint32_t v) { uint32_t r; asm("max.u32 %0, %1, 1;" : "=r"(r) : "r"(v)); return r; }
__device__ __forceinline__ float rcp(float x) { float r; asm("rcp.approx.ftz.f32 %0, %1;" : "=f"(r) : "f"(x)); return r; }
__device__ __forceinline__ uint2 ld_relaxed2(const void* p) { uint2 v; asm volatile("ld.relaxed.gpu.global.v2.u32 {%0,%1}, [%2];" : "=r"(v.x), "=r"(v.y) : "l"(p) : "memory"); return v; }
__device__ __forceinline__ void st_relaxed2(void* p, uint32_t x, uint32_t y) { asm volatile("st.relaxed.gpu.global.v2.u32 [%0], {%1,%2};" ::"l"(p), "r"(max(x, 1u)), "r"(max(y, 1u)) : "memory"); }
__host__ __device__ constexpr uint64_t dconst(uint32_t lbo, uint32_t sbo, uint32_t swz) {
    return ((uint64_t)(lbo >> 4) << 16) | ((uint64_t)(sbo >> 4) << 32) | ((uint64_t)swz << 62);
}
__device__ __forceinline__ uint32_t mkdesc(uint32_t addr, uint64_t c) { return (uint32_t)c | ((addr & 0x3FFFF) >> 4); }
#define WG_FENCE() asm volatile("wgmma.fence.sync.aligned;" ::: "memory")
#define WG_COMMIT() asm volatile("wgmma.commit_group.sync.aligned;" ::: "memory")
#define WG_WAIT(n) asm volatile("wgmma.wait_group.sync.aligned %0;" ::"n"(n) : "memory")
template <int N> __device__ __forceinline__ void reg_fence(float* d) {
#pragma unroll
    for (int i = 0; i < N; i++) asm volatile("" : "+f"(d[i])::"memory");
}
template <int N> __device__ __forceinline__ void reg_def(float* d) {
#pragma unroll
    for (int i = 0; i < N; i++) asm volatile("" : "=f"(d[i]));
}
template <int N> __device__ __forceinline__ void reg_def(uint32_t* d) {
#pragma unroll
    for (int i = 0; i < N; i++) asm volatile("" : "=r"(d[i]));
}
__device__ __forceinline__ bool is_unset(uint4 v) { return min(min(v.x, v.y), min(v.z, v.w)) == 0u; }
__device__ __forceinline__ uint4 nz4(uint32_t a, uint32_t b, uint32_t c, uint32_t d) { return make_uint4(max(a, 1u), max(b, 1u), max(c, 1u), max(d, 1u)); }
__device__ __forceinline__ void wait_flags(const uint32_t* p, uint32_t target, uint32_t mask) {
    int n = 0;
    while (~__ballot_sync(~0u, (int)(ld_relaxed(p) - target) >= 0) & mask) { if (++n > SPIN_LIMIT) __trap(); }
    asm volatile("fence.acquire.gpu;" ::: "memory");
}
__device__ __forceinline__ float silu_bf(uint32_t cbits) {
    const float c = __uint_as_float(cbits << 16);
    return bf_round(__fdividef(c, 1.f + fminf(ex2(-1.4426950408889634f * c), 1e30f)));
}
__device__ __forceinline__ void gemv_part(uint32_t wmbuf, int wp, int lane) {
    const uint32_t wa = wmbuf + wp * 512 + (8 * (lane >> 4) + (lane & 7)) * 32 + ((lane >> 3) & 1) * 16;
    float d[4] = {};
#pragma unroll
    for (int i = 0; i < 4; i++) {
        uint32_t A[4];
        const float2 v = lds2f(wmbuf + 28672 + (wp + 8 * i) * 32 + (lane & 3) * 8);
        ldsm4t(wa + (i < 3 || wp < 4 ? i : 0) * 4096, A);
        mma16816(d, A[0], A[1], A[2], A[3], __float_as_uint(v.x), __float_as_uint(v.y));
    }
    if ((lane & 3) == 0) {
        sts1(wmbuf + 29696 + (wp * 16 + (lane >> 2)) * 4, __float_as_uint(d[0]));
        sts1(wmbuf + 29696 + (wp * 16 + 8 + (lane >> 2)) * 4, __float_as_uint(d[2]));
    }
}
__device__ __forceinline__ uint32_t mod_word(float v, int col, uint32_t target) {
    v = bf_round(v);
    if ((col >= DM && col < 2 * DM) || (col >= 4 * DM && col < 5 * DM)) v += 1.f;
    return (pack2(v, 0.f) << 16) | (target & 0xFFFFu);
}
__device__ __forceinline__ const uint4* mod_src(int i, int r, int j, bool p2) {
    i = min(i, p2 ? 251 : 223);
    return (const uint4*)g_mod + (r & 7) * (6 * DM / 4) + (i < 224 ? (p2 ? 336 : 0) + i : (i < 238 ? 14 * j + i : 14 * j + i + 322));
}
__device__ __forceinline__ void mod_store(uint32_t sb, uint4 v, const uint4* src, int i) {
    const uint32_t tag = lds1(sb + M_EPOCH) + 1;
    while (__any_sync(~0u, (((v.x ^ tag) | (v.y ^ tag) | (v.z ^ tag) | (v.w ^ tag)) & 0xFFFFu) != 0u)) v = ld_relaxed4(src);
    if (i < 224) {
        const int isc = i >= 112, c4 = i - 112 * isc;
        const uint32_t a = sb + M_ST + (c4 >> 2) * 64 + (c4 & 1) * 32 + (c4 & 2) * 4 + (isc ? 0 : 4);
        sts1(a, __byte_perm(v.x, v.y, 0x7632));
        sts1(a + 16, __byte_perm(v.z, v.w, 0x7632));
    } else if (i < 252) {
        sts4(sb + M_G + (i - 224) * 16, make_uint4(v.x & 0xFFFF0000u, v.y & 0xFFFF0000u, v.z & 0xFFFF0000u, v.w & 0xFFFF0000u));
    }
}
__device__ __forceinline__ int pass_f(int fs, int ps) { return 224 * fs + ((fs & 1) ? (ps == 0 ? 96 : ps == 1 ? 32 : 0) : (ps == 0 ? 0 : ps == 1 ? 128 : 192)); }
__device__ __forceinline__ constexpr uint32_t slot_off(int l) { return l * 16384; }
__device__ __forceinline__ constexpr int g1_slot(int s) { return s % 7; }
__device__ __noinline__ void x1_fix(const uint32_t* g, uint32_t sa, int s) {
#pragma unroll 1
    for (int k = 4 * s; k < 4 * s + 4;) {
        const uint4 v = ld_relaxed4((const uint4*)(g + k * 256));
        sts4(sa + k * 1024, v);
        k += 2 * __all_sync(~0u, min(min(v.x, v.y), min(v.z, v.w)) != 0u);
    }
    __syncwarp();
}
struct LnRow { uint32_t nm, hi, lo; };
__device__ __forceinline__ LnRow ln_coeffs(float mean, float msq) {
    const float var = bf_round(fmaxf(msq - mean * mean, 0.f));
    float sd;
    asm("sqrt.approx.f32 %0, %1;" : "=f"(sd) : "f"(bf_round(var + 1e-5f)));
    const float inv = rcp(bf_round(sd)), hi = bf_round(inv);
    LnRow c;
    c.nm = pack2(-mean, -mean);
    c.hi = pack2(hi, hi);
    c.lo = pack2(inv - hi, inv - hi);
    return c;
}
__device__ __forceinline__ uint32_t hadd2(uint32_t a, uint32_t b) { uint32_t r; asm("add.rn.bf16x2 %0, %1, %2;" : "=r"(r) : "r"(a), "r"(b)); return r; }
__device__ __forceinline__ uint32_t ln_norm(uint32_t x, const LnRow& c) {
    const uint32_t d = hadd2(x, c.nm);
    return hfma2(d, c.hi, hmul2(d, c.lo));
}
__device__ __forceinline__ uint32_t ln_mod(uint32_t y, uint32_t sc, uint32_t sh) {
    return hadd2(hmul2(y, sc), sh);
}

#define LOADW bulk_e(dst, g_wd + (size_t)((f >> 5) * 4 + nq) * 1792, 7168, bar);
template <int sec> __device__ __forceinline__ void ring_loader(const Params& p, uint32_t sb_, int r_, int j_, int lane) {
    const uint32_t sb = opaque(sb_);
    const int r = opaque(r_), j = opaque(j_), nq = j >> 1, fs = 4 * (j & 1) + nq;
    const int fa = pass_f(fs, 0), fb = pass_f(fs, 1), fc = pass_f(fs, 2);
    const uint32_t* h2src = (const uint32_t*)__shfl_sync(~0u, (unsigned long long)(p.actb + (size_t)r * RB_WORDS + RB_H2), 0);
    const CUtensorMap* gmap = (const CUtensorMap*)__shfl_sync(~0u, (unsigned long long)(&p.ga + sec), 0);
#define BAR(i) (sb + M_BAR + 8 * (i))
#define kh (j & 1)
            int sl = 0;
#pragma unroll 1
            for (int s = 0; s < 28; s++) {
                if (s == 7) { wait_flags(g_flag + (8 * r + j) * 128 + 96 + lane, lds1(sb + M_EPOCH) + 1, 0xFFFFu); fence_async_global(); }
                const int ps = s < 14 ? 0 : s < 21 ? 1 : 2;
                const uint32_t half = ps < 2 ? 8192 : 4096;
                const int sp = sl;
                if (s >= PACE && s < PACE_END) mbar_wait(BAR(B_FULL + s - PACE), 0);
                mbar_wait(BAR(B_EMPTY + sp), (s >= 7 && s < 14) || s >= 21);
                expect_e(BAR(B_FULL + sp), half);
                tma3_e(sb + slot_off(sp) + sec * half, gmap + 2 * ps, 0, ps ? 64 * sl : 32 * s, ps == 0 ? fa >> 6 : ps == 1 ? fb >> 6 : fc >> 5, BAR(B_FULL + sp));
                sl = sl == 6 ? 0 : sl + 1;
            }
            if (!sec) PROFH(3);
#pragma unroll 1
            for (int e = 0; e < 4; e++) {
                const uint32_t dst = sb + slot_off(e) + sec * 8192, bar = BAR(B_FULL + e);
                const int f = (e < 2 ? fa + 64 * e : e == 2 ? fb : fc) + 32 * sec;
                mbar_wait(BAR(B_EMPTY + e), 0);
                expect_e(bar, e == 3 && sec ? 0 : 7168);
                if (!(e == 3 && sec)) { LOADW }
            }
            sl = 4;
            int e = 4;
#pragma unroll 1
            for (int grp = 0; grp < 9; grp++) {
                const int ps = grp >= 6 ? 2 : grp >= 3 ? 1 : 0;
                int sidx = grp - 3 * ps;
                if (sec && sidx == 0) { mbar_wait(BAR(B_HRDY + ps), 0); fence_async_global(); }
                sidx += sidx >= nq;
                int f = pass_f(4 * kh + sidx, ps);
#pragma unroll 1
                for (int k = 4 >> ps; k > 0; k--, e++, f += 32) {
                    const uint32_t dst = sb + slot_off(sl), bar = BAR(B_FULL + sl);
                    mbar_wait(BAR(B_EMPTY + sl), e >= 12 && e < 24);
                    if (e < WIN_END && e >= WIN) mbar_wait(BAR(B_FULL + (sl >= WIN ? sl - WIN : sl + 12 - WIN)), e - WIN >= 12);
                    expect_e(bar, sec ? 8192 : 7168);
                    if (!sec) { LOADW }
                    else bulk_e(dst + 8192, h2src + f * 64, 8192, bar);
                    sl = sl == 11 ? 0 : sl + 1;
                }
            }
            if (!sec) PROFH(4);
}

#define PROF_PARAMS
#define PROF_ARGS
__device__ __noinline__ void helper_late(const Params& p, int r_, int j_, int warp_ PROF_PARAMS) {
    extern __shared__ __align__(1024) unsigned char smem[];
    const uint32_t sb = (uint32_t)__cvta_generic_to_shared(smem);
    const int r = opaque(r_), j = opaque(j_), warp = opaque(warp_), nq = j >> 1, b = 8 * r + j;
    uint32_t* const act = (uint32_t*)__shfl_sync(~0u, (unsigned long long)(p.actb + (size_t)r * RB_WORDS), 0);
    {
        const int lane = fresh_tid() & 31;
        const uint32_t target = lds1(sb + M_EPOCH) + 1;
        if (warp == 8) { expect_e(BAR(B_XCH), 14336); expect_e(BAR(B_XCH + 1), 14336); }
            if (warp == 9) {
#pragma unroll 1
                for (int kv = 0; kv < 2; kv++) {
                    mbar_wait(BAR(B_PUB + kv), 0);
                    wait_flags(g_flag + b * 128 + lane, target, (r >= 2 ? 6u : r == 1 ? 2u : 0u) << (8 * kv));
                    fence_async_global();
                    const uint32_t dst = sb + OFF_Y + (kv ? Y_VR : Y_K);
                    expect_e(BAR(B_KRFULL + kv), r >= 2 ? 28672 : r == 1 ? 14336 : 0);
                    if (r >= 2) bulk_e(dst, act - 2 * RB_WORDS + RB_KV + j * 7168 + kv * 3584, 14336, BAR(B_KRFULL + kv));
                    if (r >= 1) bulk_e(dst + 14336, act - RB_WORDS + RB_KV + j * 7168 + kv * 3584, 14336, BAR(B_KRFULL + kv));
                    if (kv == 0) { PROFH(8); }
                }
            } else if (warp == 8) {
                uint4 v[8];
                mbar_wait(BAR(B_WOFULL), 0);
#pragma unroll
                for (int k = 0; k < 8; k++) v[k] = ld_relaxed4(mod_src(lane + 32 * k, r, j, true));
#pragma unroll
                for (int k = 0; k < 8; k++) mod_store(sb, v[k], mod_src(lane + 32 * k, r, j, true), lane + 32 * k);
                warp_arrive(BAR(B_MOD1));
            } else if (warp == 11) {
                if (kh == 1 && r < 14) {
                    const uint32_t wmbuf = sb + OFF_X + HALF;
                    const int mcol = 2 * DM + 32 * (4 * r + nq);
                    mbar_wait(BAR(B_XFREE), 0);
                    tma3_e(wmbuf, &p.wm2, mcol, 0, 0, BAR(B_WMFULL));
                    tma3_e(wmbuf + 14336, &p.wm2, mcol, 224, 0, BAR(B_WMFULL));
#pragma unroll 1
                    for (int wd = lane; wd < 224; wd += 32) {
                        const uint32_t cb = __ldg((const uint32_t*)p.c + wd);
                        sts1(wmbuf + 28672 + (wd >> 3) * 32 + (wd & 3) * 8 + (wd & 4), pack2(silu_bf(cb & 0xFFFFu), silu_bf(cb >> 16)));
                    }
                    __syncwarp();
                    mbar_wait(BAR(B_WMFULL), 0);
                    const uint32_t wa = wmbuf + (8 * (lane >> 4) + (lane & 7)) * 64 + ((lane >> 3) & 1) * 16;
                    float d[2][4] = {};
#pragma unroll 4
                    for (int ks = 0; ks < 28; ks++) {
                        uint32_t A[8];
                        ldsm4t(wa + ks * 1024, A); ldsm4t(wa + ks * 1024 + 32, A + 4);
                        const float2 v = lds2f(wmbuf + 28672 + ks * 32 + (lane & 3) * 8);
                        mma16816(d[0], A[0], A[1], A[2], A[3], __float_as_uint(v.x), __float_as_uint(v.y));
                        mma16816(d[1], A[4], A[5], A[6], A[7], __float_as_uint(v.x), __float_as_uint(v.y));
                    }
                    const int q = lane & 3, col = mcol + 8 * q + (lane >> 2);
                    const uint32_t word = mod_word(q == 0 ? d[0][0] : q == 1 ? d[0][2] : q == 2 ? d[1][0] : d[1][2], col, target);
#pragma unroll
                    for (int i = 0; i < 8; i++) st_relaxed(g_mod + i * 6 * DM + col, word);
                }
                warp_arrive(BAR(B_WMFREE));
                mbar_wait(BAR(B_VRFULL), 0);
                l2_prefetch_e((const char*)p.wg + (size_t)b * 12544, 12544);
                l2_prefetch_e((const char*)p.wu + (size_t)b * 12544, 12544);
#pragma unroll 1
                for (int k = 0; k < (r < 12 ? 2 : 1); k++) {
                    const int u = 28 * kh + r + 16 * k;
                    expect_e(BAR(B_XFULL + k), 7168);
                    tma3_e(sb + OFF_Y + 102400, &p.dn, 0, 32 * u, 7 * j, BAR(B_XFULL + k));
                    tma3_e(sb + OFF_Y + 102400 + 3584, &p.dn, 0, 32 * u, 7 * (j ^ 1), BAR(B_XFULL + k));
                    mbar_wait(BAR(B_XFULL + k), 1);
                    asm volatile("{\n.reg .pred p;\nelect.sync _|p, 0xffffffff;\n@p cp.async.bulk.global.shared::cta.bulk_group [%0], [%1], 7168;\n"
                                 "cp.async.bulk.commit_group;\ncp.async.bulk.wait_group 0;\n}" ::"l"(g_wd + (size_t)(u * 4 + nq) * 1792), "r"(sb + OFF_Y + 102400) : "memory");
                    __syncwarp();
                }
                warp_arrive(BAR(B_FULLK));
                fence_gpu();
                if (lane < 16) st_relaxed(g_flag + (8 * lane + j) * 128 + 96 + r, target);
            }
        if (warp == 8 || warp == 11) {
            const int sec = warp == 11;
            if (sec) ring_loader<1>(p, sb, r, j, lane); else ring_loader<0>(p, sb, r, j, lane);
            mbar_wait(BAR(B_DONE), 0);
        } else if (warp == 9) {
#pragma unroll
            for (int ev = 0; ev < 4; ev++) { expect_e(BAR(B_GFULL + ev), ev < 2 ? HALF / 2 : 16384 + 4096); expect_e(BAR(B_XFULL + 2 + ev), ev < 2 ? HALF / 2 : HALF - 16384); }
            mbar_wait(BAR(B_PUB + 2), 0);
            const uint32_t* fp = g_flag + b * 128 + 32 + lane;
            const int par = (target - 1) & 1;
#pragma unroll 1
            for (int n = 0, ev = 0; ev < 4; n++) {
                if (ev == 1) mbar_wait(BAR(B_PUB + 3), 0);
                uint32_t ok = __ballot_sync(~0u, (int)(ld_relaxed(fp) - target) >= 0) >> (8 * ev);
                while ((ok & 0xFFu) == 0xFFu) {
                    if (ev == 1) mbar_wait(BAR(B_FULLK), 1);
                    asm volatile("fence.acquire.gpu;" ::: "memory");
                    fence_async_global();
                    const int tile = (ev & 1) + (ev >> 1) * par * 2;
                    const uint32_t dst = sb + (ev == 0 ? OFF_X : OFF_Y + (ev & 1) * HALF), first = ev < 2 ? HALF / 2 : 16384;
                    const char* src = (const char*)(act + RB_O + ((ev >> 1) * 2 + tile) * 14336);
                    if (ev >= 2) bulk_e(sb + OFF_X + X_STAT + (ev & 1) * 49152, act + RB_ST + tile * 1024, 4096, BAR(B_GFULL + ev));
                    bulk_e(dst, src, first, BAR(B_GFULL + ev));
                    bulk_e(dst + first, src + first, HALF - first, BAR(B_XFULL + 2 + ev));
                    if (ev) PROFH(4 + ev);
                    ev++; ok >>= 8;
                }
                if (n > SPIN_LIMIT) __trap();
            }
            mbar_wait(BAR(B_XFULL + 5), 1);
#pragma unroll 1
            for (int hf = 0; hf < 2; hf++) {
                const int tile = (par ^ 1) * 2 + hf;
                uint4* xz = (uint4*)(act + RB_X1 + tile * 14336 + j * 1792) + lane;
#pragma unroll
                for (int i = 0; i < 14; i++) xz[i * 32] = make_uint4(0, 0, 0, 0);
                ((uint4*)(act + RB_ST + (tile * 8 + j) * 128))[lane] = make_uint4(0, 0, 0, 0);
            }
#pragma unroll 1
            for (int ps = 0; ps < 3; ps++) {
                mbar_wait(BAR(B_PUB + 6 + ps), 0);
                wait_flags(g_flag + b * 128 + 64 + lane, target, (0x55u << kh) << (8 * ps));
                warp_arrive(BAR(B_HRDY + ps));
                PROFH(9 + ps);
            }
        } else {
#pragma unroll 1
            for (int k = 0; k < 9; k++) {
                uint32_t* fp = k < 2 ? g_flag + (b + 8 * lane) * 128 + k * 8 + lane : g_flag + (8 * r + lane) * 128 + 16 + k * 8 + j;
                mbar_wait(BAR(B_PUB + k), 0);
                if (k != 4 && k != 5) fence_gpu();
                if (k < 2 ? (lane == 1 || lane == 2) : lane < 8) st_relaxed(fp, target);
                if (k >= 3 && k <= 5) PROFH(k - 3);
            }
        }
    }
}

__global__ void __cluster_dims__(2, 1, 1) __launch_bounds__(384, 1) fused_block_kernel(const __grid_constant__ Params p) {
    extern __shared__ __align__(1024) unsigned char smem[];
    const uint32_t sb = (uint32_t)__cvta_generic_to_shared(smem);
    const int tid = threadIdx.x, lane = tid & 31, warp = __shfl_sync(~0u, tid >> 5, 0);
    const int m = blockIdx.x >> 1;
    int r, nq;
    if (m < 4) { r = 15; nq = m; }
    else if (m < 36) { r = (m - 4) & 7; nq = (m - 4) >> 3; }
    else { nq = (m - 36) / 7; r = m - 28 - 7 * nq; }
    const int j = opaque(2 * nq + (blockIdx.x & 1)), b = 8 * r + j, fs = 4 * kh + nq;
#define act (p.actb + (size_t)r * RB_WORDS)
    constexpr uint32_t sc = 0;
    if (lane == 0 && warp < 9 && warp != 6 && warp != 7) {
        const int i0 = warp == 8 ? 0 : 8 + 8 * warp, cnt = warp == 0 || warp == 8 ? 1 : warp < 3 ? 2 : 8;
#pragma unroll
        for (int k = 0; k < 8; k++) if (i0 + k != B_WMFULL) mbar_init(BAR(i0 + k), cnt);
        if (warp == 8) mbar_init(BAR(B_WMFULL), 1);
        asm volatile("fence.mbarrier_init.release.cluster;" ::: "memory");
        fence_async_smem();
    }

    if (warp >= 8) {
        const int lane = fresh_tid() & 31;
        const bool early = kh == 0, gemv = r < 14;
        const int mcol = early ? 16 * (4 * r + nq) : 2 * DM + 32 * (4 * r + nq);
        const uint32_t wmbuf = sb + OFF_Y + HALF;
        if (warp == 8) {
            __syncwarp();
            expect_e(BAR(B_WMFULL), gemv ? 28672 >> early : 0);
            if (early && gemv) { tma3_e(wmbuf, &p.wm, mcol, 0, 0, BAR(B_WMFULL)); tma3_e(wmbuf + 7168, &p.wm, mcol, 224, 0, BAR(B_WMFULL)); }
#pragma unroll
            for (int kb = 0; kb < XFIRST; kb++) {
                expect_e(BAR(B_XFULL + kb), 16384);
                tma3_e(sb + OFF_X + kb * 16384, &p.xm, 64 * kb, 128 * r, 0, BAR(B_XFULL + kb));
            }
        }
        asm volatile("setmaxnreg.dec.sync.aligned.u32 56;");
        if (warp == 9) {
#pragma unroll
            for (int i = 56; i < 64; i++) init_e(BAR(i), 1);
            fence_async_smem();
        }
        bar_arrive(0, 384);
        asm volatile("barrier.cluster.arrive.relaxed.aligned;" ::: "memory");
        if (warp == 8) {
#pragma unroll
            for (int kb = XFIRST; kb < 7; kb++) {
                expect_e(BAR(B_XFULL + kb), 16384);
                tma3_e(sb + OFF_X + kb * 16384, &p.xm, 64 * kb, 128 * r, 0, BAR(B_XFULL + kb));
            }
            if (KDELAY >= 0) { mbar_wait(BAR(B_XFULL + KDELAY), 0); l2_prefetch_e((const char*)p.wqkv + (size_t)b * 9408, 9408); }
#pragma unroll 1
            for (int mt = 0; mt < 4; mt++) {
                if (mt == 1) bar_sync(9, 384);
                if (mt == 3) mbar_wait(BAR(B_WMFREE), 0);
                if (mt == 1 && early) mbar_wait(BAR(B_WMFREE), 0);
                if (mt) mbar_wait(BAR(mt == 1 ? (VGATE == 1 ? B_XFREE : B_FULLK) : mt == 2 ? B_MOD1 : B_VRFULL), 0);
                const uint32_t bar = BAR(mt == 3 ? B_WOFULL : B_FULLK + mt), dst = sb + (mt < 2 ? OFF_Y : OFF_X) + (mt & 1) * HALF;
                const int c0 = (mt < 2 ? DM + DM * mt : 0) + 56 * j - 8 * kh;
                if (!sc) {
                    expect_e(bar, HALF);
                    tma3_e(dst, mt == 3 ? &p.wo : &p.qkv, c0, 0, 0, bar);
                    tma3_e(dst + HALF / 2, mt == 3 ? &p.wo : &p.qkv, c0, 224, 0, bar);
                }
            }
        } else {
            if (KDELAY < 0 && warp == 10) l2_prefetch_e((const char*)p.wqkv + (size_t)b * 9408, 9408);
            bar_sync(9, 384);
            if (sc) return;
            if (warp == 11 && early) {
                const uint32_t target = lds1(sb + M_EPOCH) + 1;
                mbar_wait(BAR(B_GEMV), 0);
                float sum = 0.f;
#pragma unroll
                for (int i = 0; i < 8; i++) sum += *(const float*)(smem + OFF_Y + HALF + 29696 + (i * 16 + (lane & 15)) * 4);
                uint32_t* mg = g_mod + mcol + (lane & 15) + (lane >> 4) * 4 * 6 * DM;
                const uint32_t word = mod_word(sum, mcol, target);
                if (gemv) { st_relaxed(mg, word); st_relaxed(mg + 6 * DM, word); st_relaxed(mg + 12 * DM, word); st_relaxed(mg + 18 * DM, word); }
            }
        }
    }
    if (LIKELY(warp < 8)) {
        const int w = warp >> 2, wi = warp & 3;
#define COORDS const int t = fresh_tid() & 127, lane = t & 31, q = lane & 3, lr = lane >> 2, ra = 64 * w + 16 * wi + lr; \
        const uint32_t lx = (lane >> 4) ^ (lane & 7), mrow = (64 * w + 16 * wi + ((lane >> 3) & 1) * 8 + (lane & 7)) * 128; \
        (void)q; (void)lr; (void)ra; (void)lx; (void)mrow;
        const int sid = 2 * (j & 3) + w;
#define RUN(k) (!sc || sid == (k))
#define WAIT(i, par) mbar_wait_c(BAR(i), (par) | sc)
        constexpr uint64_t DB128 = dconst(4096, 1024, 1);
        {
            const int wd = fresh_tid();
            const uint32_t cb = wd < 224 ? __ldg((const uint32_t*)p.c + wd) : 0u;
            if (wd == 255 && !sc) sts1(sb + M_EPOCH, atomicAdd(&g_ticket, 1u) / NCTA);
            sts1(sb + OFF_Y + HALF + 28672 + (wd >> 3) * 32 + (wd & 3) * 8 + (wd & 4), pack2(silu_bf(cb & 0xFFFFu), silu_bf(cb >> 16)));
        }
        bar_arrive(9, 384);
        bar_sync(0, 384);
        asm volatile("barrier.cluster.arrive.relaxed.aligned;" ::: "memory");
        asm volatile("setmaxnreg.inc.sync.aligned.u32 224;");
        PROFC(0);
        uint32_t xr[16];
        {
            COORDS
            uint32_t h[112];
            LnRow ca, cb;
            const int mi = min(128 * w + t, 223);
            const uint4* msrc = mod_src(mi, r, j, false);
            uint4 mv;
            {
                float ds[4] = {}, da[2][4] = {}, db[2][4] = {};
                const uint32_t ONE2 = 0x3F803F80u;
#pragma unroll
                for (int kb = 0; kb < 7; kb++) {
                    if (kb == GEMV_AT && kh == 0) { WAIT(B_WMFULL, 0); gemv_part(sb + OFF_Y + HALF, warp, lane); warp_arrive(BAR(B_GEMV)); }
                    WAIT(B_XFULL + kb, 0);
#pragma unroll
                    for (int k4 = 0; k4 < 4; k4++) ldsm4(sb + OFF_X + mrow + kb * 16384 + (((2 * k4) ^ lx) << 4), h + 16 * kb + 4 * k4);
#pragma unroll
                    for (int k4 = 0; k4 < 4; k4++) {
                        const uint32_t* f = h + 16 * kb + 4 * k4;
                        mma16816(ds, f[0], f[1], f[2], f[3], ONE2, ONE2);
                        mma1688(da[0], f[0], f[1], f[0]); mma1688(db[0], f[0], f[1], f[1]);
                        mma1688(da[1], f[2], f[3], f[2]); mma1688(db[1], f[2], f[3], f[3]);
                    }
                }
#pragma unroll
                for (int i = 0; i < 4; i++) {
                    const int ch = 7 * j + 2 * i + (lane >> 4);
                    ldsm4(sb + OFF_X + mrow + (ch >> 3) * 16384 + (((ch ^ lane) & 7) << 4), xr + 4 * i);
                }
                mv = ld_relaxed4(msrc);
                warp_arrive(BAR(B_XFREE));
                float qa = (lr & 1) ? da[0][1] + da[1][1] : da[0][0] + da[1][0];
                float qb = (lr & 1) ? db[0][3] + db[1][3] : db[0][2] + db[1][2];
                const int src = (lane & ~3) | (lr >> 1);
                qa = __shfl_sync(~0u, qa, src);
                qb = __shfl_sync(~0u, qb, src);
                ca = ln_coeffs(ds[0] * (1.f / DM), qa * (1.f / DM));
                cb = ln_coeffs(ds[2] * (1.f / DM), qb * (1.f / DM));
#pragma unroll
                for (int i = 0; i < 4 * NPRE; i += 2) { h[i] = ln_norm(h[i], ca); h[i + 1] = ln_norm(h[i + 1], cb); }
            }
            PROFC(1);
            {
                float ak[28], av[28], aq[28];
                uint32_t kp[14], vp[14];
                const uint64_t bq0 = (DB128 & ~0xFFFFFFFFull) | (mkdesc(sb + OFF_X, DB128) + kh), bk0 = bq0 + (OFF_Y >> 4), bv0 = bk0 + (HALF >> 4);
                uint32_t* kvg = act + RB_KV + j * 7168 + (8 * w + 2 * wi) * 224 + lane;
                mod_store(sb, mv, msrc, mi);
                bar_sync(3, 256);
                if (warp == 0) warp_arrive(BAR(B_MOD1));
                WAIT(B_FULLK, 0);
                PROFC(2);
                reg_def<28>(ak);
#pragma unroll
                for (int g4 = 0; g4 < 4; g4++) {
#pragma unroll
                    for (int ks = 7 * g4; ks < 7 * g4 + 7; ks++) {
                        const uint4 st = *(const uint4*)(smem + M_ST + ks * 64 + q * 16);
                        if (ks >= NPRE) {
                            h[4 * ks] = ln_norm(h[4 * ks], ca); h[4 * ks + 1] = ln_norm(h[4 * ks + 1], cb);
                            h[4 * ks + 2] = ln_norm(h[4 * ks + 2], ca); h[4 * ks + 3] = ln_norm(h[4 * ks + 3], cb);
                        }
                        h[4 * ks] = ln_mod(h[4 * ks], st.x, st.y); h[4 * ks + 1] = ln_mod(h[4 * ks + 1], st.x, st.y);
                        h[4 * ks + 2] = ln_mod(h[4 * ks + 2], st.z, st.w); h[4 * ks + 3] = ln_mod(h[4 * ks + 3], st.z, st.w);
                    }
                    WG_FENCE();
#pragma unroll
                    for (int ks = 7 * g4; ks < 7 * g4 + 7; ks++) wgmma_rl_56(ak, h[4 * ks], h[4 * ks + 1], h[4 * ks + 2], h[4 * ks + 3], bk0 + ks * 128, ks != 0);
                }
                WG_COMMIT();
                PROFC(3);
                reg_def<28>(av);
                WG_WAIT(0);
                reg_fence<28>(ak);
#pragma unroll
                for (int g = 0; g < 7; g++) {
                    kp[2 * g] = pack2(ak[4 * g], ak[4 * g + 1]); kp[2 * g + 1] = pack2(ak[4 * g + 2], ak[4 * g + 3]);
                    kvg[g * 32] = kp[2 * g]; kvg[224 + g * 32] = kp[2 * g + 1];
                }
                warp_arrive(BAR(B_PUB));
                PROFC(4);
                if (KEARLY) WAIT(B_FULLV, 0);
                WG_FENCE();
#pragma unroll
                for (int ks = KEARLY ? 0 : 8; ks < 28; ks++) wgmma_rl_56(av, h[4 * ks], h[4 * ks + 1], h[4 * ks + 2], h[4 * ks + 3], bv0 + ks * 128, ks != 0);
                WG_COMMIT();
                reg_def<28>(aq);
                WAIT(B_FULLQ, 0);
                WG_FENCE();
#pragma unroll
                for (int ks = 0; ks < VPRE; ks++) wgmma_rl_56(aq, h[4 * ks], h[4 * ks + 1], h[4 * ks + 2], h[4 * ks + 3], bq0 + ks * 128, ks != 0);
                WG_COMMIT();
                WG_WAIT(1);
                reg_fence<28>(av);
#pragma unroll
                for (int g = 0; g < 7; g++) {
                    vp[2 * g] = pack2(av[4 * g], av[4 * g + 1]); vp[2 * g + 1] = pack2(av[4 * g + 2], av[4 * g + 3]);
                    kvg[3584 + g * 32] = vp[2 * g]; kvg[3584 + 224 + g * 32] = vp[2 * g + 1];
                }
                warp_arrive(BAR(B_PUB + 1));
                PROFC(5);
                if (!VPRE) WAIT(B_FULLQ, 0);
                WG_FENCE();
#pragma unroll
                for (int ks = VPRE; ks < 28; ks++) wgmma_rl_56(aq, h[4 * ks], h[4 * ks + 1], h[4 * ks + 2], h[4 * ks + 3], bq0 + ks * 128, ks != 0);
                WG_COMMIT();
                WAIT(B_PUB + 1, 0);
                const uint32_t rg = 8 * w + 2 * wi + ((lane >> 3) & 1);
                const uint32_t ko = sb + OFF_Y + Y_KOWN + rg * 896 + (lane & 7) * 16, qo = sb + OFF_Y + Y_Q + rg * 1024 + (lane >> 4) * 128 + (lane & 7) * 16;
#pragma unroll
                for (int g = 0; g < 6; g += 2) {
                    stsm4(ko + (g + (lane >> 4)) * 128, kp[2 * g], kp[2 * g + 1], kp[2 * g + 2], kp[2 * g + 3]);
                    stsm4(ko + (Y_VOWN - Y_KOWN) + (g + (lane >> 4)) * 128, vp[2 * g], vp[2 * g + 1], vp[2 * g + 2], vp[2 * g + 3]);
                }
                stsm4(ko + (lane >> 4) * (Y_VOWN - Y_KOWN) + 6 * 128, kp[12], kp[13], vp[12], vp[13]);
                WG_WAIT(0);
                reg_fence<28>(aq);
                __syncwarp();
                if (lane < 3 && w == 1) mbar_arrive(BAR(B_EMPTY + lane));
                uint32_t qp[14];
#pragma unroll
                for (int i = 0; i < 14; i++) qp[i] = pack2(aq[2 * i], aq[2 * i + 1]);
                stsm4(qo, qp[0], qp[1], qp[2], qp[3]);
                stsm4(qo + 256, qp[4], qp[5], q < 2 ? qp[6] : 0u, q < 2 ? qp[7] : 0u);
                stsm4(qo + 512, q < 2 ? 0u : qp[6], q < 2 ? 0u : qp[7], qp[8], qp[9]);
                stsm4(qo + 768, qp[10], qp[11], qp[12], qp[13]);
                fence_async_smem();
                if (!sc) bar_sync(3, 256);
            }
        }
        PROFC(6);
        WAIT(B_KRFULL, 0);
        if (ATT_OFF && w == ATT_WG) { const uint32_t t0 = clock(); while (clock() - t0 < ATT_OFF) {} }
        PROFC(7);
        if (RUN(2)) {
#pragma unroll 1
            for (int hf = sc; hf < 2; hf++) {
                COORDS
                float s[160];
                const float CS = 0.18898223650461361f * 1.4426950408889634f;
                const float NEG = __int_as_float(0xFF800000);
                constexpr uint64_t DQ = dconst(128, 1024, 0), DK = dconst(128, 896, 0);
                {
                    const uint32_t qd = mkdesc(sb + OFF_Y + Y_Q + hf * 8192 + w * 512, DQ), kd = mkdesc(sb + OFF_Y + Y_K + hf * 8 * 896 + w * 384, DK);
                    reg_def<160>(s);
                    WG_FENCE();
                    wgmma_sk_160<DQ, DK>(s, qd, kd, 0);
                    wgmma_sk_160<DQ, DK>(s, qd + 16, kd + 16, 1);
                    wgmma_sk_160<DQ, DK>(s + 80, qd, kd + 20 * 56, 0);
                    wgmma_sk_160<DQ, DK>(s + 80, qd + 16, kd + 20 * 56 + 16, 1);
                    WG_COMMIT();
                    WG_WAIT(0);
                    reg_fence<160>(s);
                }
                if (r < 2) {
                    const int pmin = 4 - 2 * r - hf;
#pragma unroll
                    for (int p4 = 0; p4 < 4; p4++)
                        if (p4 < pmin) {
#pragma unroll
                            for (int i = 0; i < 32; i++) asm volatile("mov.b32 %0, 0xFF800000;" : "=f"(s[32 * p4 + i]));
                        }
                }
                const bool c0 = 2 * q > lr, c1 = 2 * q + 1 > lr;
#pragma unroll
                for (int pp = 0; pp < 4; pp++) {
                    const bool me = pp == wi;
                    float* e = s + 8 * pp;
                    if (me && !c0) { e[0] = NEG; e[6] = NEG; }
                    if (me && !c1) { e[1] = NEG; e[7] = NEG; }
                    if (me) { e[2] = NEG; e[3] = NEG; }
                    e = s + 8 * (pp + 16);
                    if (me && c0) { e[0] = NEG; e[6] = NEG; }
                    if (me && c1) { e[1] = NEG; e[7] = NEG; }
                    if (me) { e[4] = NEG; e[5] = NEG; }
                }
#pragma unroll
                for (int i = 0; i < 24; i++) s[i] = (i >> 3) < wi ? s[136 + i] : s[i];
                int i0 = 0x80000000, i1 = 0x80000000, i2 = 0x80000000, i3 = 0x80000000;
#pragma unroll
                for (int pp = 0; pp < 17; pp++) {
                    const float* e = s + 8 * pp;
                    i0 = __vimax3_s32(i0, __float_as_int(e[0]), __float_as_int(e[1])); i1 = __vimax3_s32(i1, __float_as_int(e[2]), __float_as_int(e[3]));
                    i2 = __vimax3_s32(i2, __float_as_int(e[4]), __float_as_int(e[5])); i3 = __vimax3_s32(i3, __float_as_int(e[6]), __float_as_int(e[7]));
                }
                i0 = max(i0, i2); i1 = max(i1, i3);
                i0 = max(i0, __shfl_xor_sync(~0u, i0, 1)); i1 = max(i1, __shfl_xor_sync(~0u, i1, 1));
                i0 = max(i0, __shfl_xor_sync(~0u, i0, 2)); i1 = max(i1, __shfl_xor_sync(~0u, i1, 2));
                if (__any_sync(~0u, (i0 | i1) < 0)) {
                    uint32_t u0 = ~0u, u1 = ~0u, u2 = ~0u, u3 = ~0u;
#pragma unroll
                    for (int pp = 0; pp < 17; pp++) {
                        const float* e = s + 8 * pp;
                        u0 = __vimin3_u32(u0, __float_as_uint(e[0]), __float_as_uint(e[1])); u1 = __vimin3_u32(u1, __float_as_uint(e[2]), __float_as_uint(e[3]));
                        u2 = __vimin3_u32(u2, __float_as_uint(e[4]), __float_as_uint(e[5])); u3 = __vimin3_u32(u3, __float_as_uint(e[6]), __float_as_uint(e[7]));
                    }
                    u0 = min(u0, u2); u1 = min(u1, u3);
                    u0 = min(u0, __shfl_xor_sync(~0u, u0, 1)); u1 = min(u1, __shfl_xor_sync(~0u, u1, 1));
                    u0 = min(u0, __shfl_xor_sync(~0u, u0, 2)); u1 = min(u1, __shfl_xor_sync(~0u, u1, 2));
                    if (i0 < 0) i0 = u0;
                    if (i1 < 0) i1 = u1;
                }
                const float ma = __int_as_float(i0), mb = __int_as_float(i1);
                const float na = -ma * CS, nb = -mb * CS;
                PROFC(8 + 3 * hf);
                {
                    WAIT(B_VRFULL, 0);
                    float o[16] = {}, rs[4] = {};
                    const uint32_t va = sb + OFF_Y + Y_VR + (8 * hf + ((lane >> 3) & 1)) * 896 + (3 * w + (lane >> 4)) * 128 + (lane & 7) * 16;
                    constexpr uint32_t OWN = Y_VOWN - 32 * 896;
#pragma unroll
                    for (int pp = 0; pp < 17; pp++) {
                        uint32_t B[8];
                        const uint32_t v = va + pp * 1792 + (pp < 3 ? (pp < wi ? 17 * 1792 + OWN : 0) : pp == 16 ? OWN : pp >= 12 ? hf * OWN : 0);
                        ldsm4t(v, B); ldsm4t(v + 256, B + 4);
                        float e[8];
#pragma unroll
                        for (int i = 0; i < 8; i++) e[i] = ex2(fmaf(s[8 * pp + i], CS, (i & 2) ? nb : na));
                        const uint32_t p0 = pack2(e[0], e[1]), p1 = pack2(e[2], e[3]), p2 = pack2(e[4], e[5]), p3 = pack2(e[6], e[7]);
                        mma16816(rs, p0, p1, p2, p3, 0x3F803F80u, 0x3F803F80u);
#pragma unroll
                        for (int g = 0; g < 4; g++) mma16816(o + 4 * g, p0, p1, p2, p3, B[2 * g], B[2 * g + 1]);
                    }
                    PROFC(9 + 3 * hf);
                    const float ia = rcp(rs[0]), ib = rcp(rs[2]);
                    uint32_t* og = act + RB_O + hf * 14336 + (7 * j + 3 * w) * 256 + wi * 64 + lane;
#pragma unroll
                    for (int g = 0; g < 4; g++) {
                        if ((g == 3 - 3 * w) ? ((q >> 1) == w) : true) {
                            og[g * 256] = pack2(o[4 * g] * ia, o[4 * g + 1] * ia);
                            og[g * 256 + 32] = pack2(o[4 * g + 2] * ib, o[4 * g + 3] * ib);
                        }
                    }
                    warp_arrive(BAR(B_PUB + 2 + hf));
                    PROFC(10 + 3 * hf);
                }
            }
        }
        uint32_t x1p[14];
        COORDS
        constexpr uint64_t DT = dconst(1024, 128, 0);
        const int tile = opaque((lds1(sb + M_EPOCH) & 1) * 2 + w);
        if (RUN(4)) {
            float ac[28];
            const uint32_t ad = mkdesc(sb + (w ? OFF_Y + HALF : OFF_X), DT), bd = mkdesc(sb + OFF_X + HALF, DB128) + kh;
            WAIT(B_WOFULL, 0);
            WAIT(B_MOD1, 1);
            WAIT(B_GFULL + w, 0);
            PROFC(28);
            reg_def<28>(ac);
#pragma unroll 1
            for (int u = 0; u < 4; u++) {
                if (u == 2) WAIT(B_XFULL + 2 + w, 1);
                WG_FENCE();
#pragma unroll
                for (int i = 0; i < 7; i++) wgmma_ss_56<DT, DB128>(ac, ad + (7 * u + i) * 128, bd + (7 * u + i) * 128, (u | i) != 0);
            }
            WG_COMMIT();
            WG_WAIT(0);
            reg_fence<28>(ac);
            PROFC(14);
            __syncwarp();
            if (lane < 3) mbar_arrive(BAR(B_EMPTY + 4 - w + lane));
            if (lane < 3 && w == 0) mbar_arrive(BAR(B_EMPTY + lane));
            float ds[4] = {}, da[4] = {}, db[4] = {};
            uint32_t* xo = act + RB_X1 + tile * 14336 + 7 * j * 256 + wi * 64 + lane;
#pragma unroll
            for (int g = 0; g < 7; g++) {
                const float2 ga = *(const float2*)(smem + M_G + (8 * g + 2 * q) * 4);
                x1p[2 * g] = pack2(fmaf(ga.x, ac[4 * g], bf_lo(xr[2 * g])), fmaf(ga.y, ac[4 * g + 1], bf_hi(xr[2 * g])));
                x1p[2 * g + 1] = pack2(fmaf(ga.x, ac[4 * g + 2], bf_lo(xr[2 * g + 1])), fmaf(ga.y, ac[4 * g + 3], bf_hi(xr[2 * g + 1])));
                st_relaxed(xo + g * 256, nz(x1p[2 * g])); st_relaxed(xo + g * 256 + 32, nz(x1p[2 * g + 1]));
                mma1688(ds, x1p[2 * g], x1p[2 * g + 1], 0x3F803F80u);
                mma1688(da, x1p[2 * g], x1p[2 * g + 1], x1p[2 * g]);
                mma1688(db, x1p[2 * g], x1p[2 * g + 1], x1p[2 * g + 1]);
            }
            const int src = (lane & ~3) | (lr >> 1);
            const float qa = __shfl_sync(~0u, (lr & 1) ? da[1] : da[0], src), qb = __shfl_sync(~0u, (lr & 1) ? db[3] : db[2], src);
            const float kk = (q & 1) ? ((q & 2) ? qb : qa) : ((q & 2) ? ds[2] : ds[0]);
            st_relaxed(act + RB_ST + ((tile * 8 + j) * 64 + 16 * wi + lr + 4 * (q & 2)) * 2 + (q & 1), nz(__float_as_uint(kk)));
            __syncwarp();
            if (lane < 2) mbar_arrive(BAR(B_PUB + 4 + w));
        } else reg_def<14>(x1p);
        PROFC(15);
        uint32_t h2a[32], h2b[24];
        {
            const int fa = pass_f(fs, 0), fb = pass_f(fs, 1), fc = pass_f(fs, 2);
            uint32_t* h2g = act + RB_H2 + (8 * w + 2 * wi) * 32 + lane;
            const uint32_t a0 = mkdesc(sb + OFF_Y + w * HALF, DT);
            if (RUN(3)) {
                LnRow ca, cb;
                {
                    const uint32_t* sg = act + RB_ST + ((tile * 8 + 2 * q) * 64 + 16 * wi + lr) * 2;
                    uint2 u[4];
                    WAIT(B_GFULL + 2 + w, 0);
                    PROFC(16);
#pragma unroll
                    for (int i = 0; i < 4; i++) { const float2 v = lds2f(sb + OFF_X + X_STAT + w * 49152 + ((2 * q + (i >> 1)) * 64 + 16 * wi + lr + 8 * (i & 1)) * 8); u[i] = make_uint2(__float_as_uint(v.x), __float_as_uint(v.y)); }
                    while (__any_sync(~0u, min(min(min(u[0].x, u[0].y), min(u[1].x, u[1].y)), min(min(u[2].x, u[2].y), min(u[3].x, u[3].y))) < 1u - sc)) {
#pragma unroll
                        for (int i = 0; i < 4; i++) u[i] = ld_relaxed2(sg + (i >> 1) * 128 + (i & 1) * 16);
                    }
                    warp_arrive(BAR(B_EMPTY + 3 + 3 * w));
                    float v[4] = {__uint_as_float(u[0].x) + __uint_as_float(u[2].x), __uint_as_float(u[0].y) + __uint_as_float(u[2].y),
                                  __uint_as_float(u[1].x) + __uint_as_float(u[3].x), __uint_as_float(u[1].y) + __uint_as_float(u[3].y)};
#pragma unroll
                    for (int i = 0; i < 4; i++) { v[i] += __shfl_xor_sync(~0u, v[i], 1); v[i] += __shfl_xor_sync(~0u, v[i], 2); }
                    ca = ln_coeffs(v[0] * (1.f / DM), v[1] * (1.f / DM));
                    cb = ln_coeffs(v[2] * (1.f / DM), v[3] * (1.f / DM));
                }
                const uint32_t ha = sb + OFF_Y + w * HALF + (lane >> 4) * 1024 + (2 * wi + ((lane >> 3) & 1)) * 128 + (lane & 7) * 16;
                const uint32_t sta = sb + M_ST + q * 16;
                const uint32_t* xg = act + RB_X1 + tile * 14336 + (lane >> 4) * 256 + wi * 64 + (lane & 15) * 4;
                uint32_t x[8];
                const uint32_t xs = sb + OFF_Y + w * HALF + (lane >> 4) * 1024 + wi * 256 + (lane & 15) * 16;
                uint4 st[2];
                auto load = [&](int s) {
                    if (s == 4) mbar_wait_c(BAR(B_XFULL + 4 + w), 1);
                    ldsm4(ha + s * 4096, x); ldsm4(ha + s * 4096 + 2048, x + 4);
                    st[0] = lds4(sta + s * 128); st[1] = lds4(sta + s * 128 + 64);
                };
                auto prep = [&](int s, uint32_t* f) {
                    if (__any_sync(~0u, min(min(min(x[0], x[1]), min(x[2], x[3])), min(min(x[4], x[5]), min(x[6], x[7]))) < 1u - sc)) {
                        WG_WAIT(0);
                        x1_fix(xg, xs, s);
                        ldsm4(ha + s * 4096, x); ldsm4(ha + s * 4096 + 2048, x + 4);
                    }
#pragma unroll
                    for (int i = 0; i < 2; i++) {
                        f[4 * i] = ln_mod(ln_norm(x[4 * i], ca), st[i].x, st[i].y); f[4 * i + 1] = ln_mod(ln_norm(x[4 * i + 1], cb), st[i].x, st[i].y);
                        f[4 * i + 2] = ln_mod(ln_norm(x[4 * i + 2], ca), st[i].z, st[i].w); f[4 * i + 3] = ln_mod(ln_norm(x[4 * i + 3], cb), st[i].z, st[i].w);
                    }
                    if (s < 13) load(s + 1);
                    stsm4(ha + s * 4096, f[0], f[1], f[2], f[3]); stsm4(ha + s * 4096 + 2048, f[4], f[5], f[6], f[7]);
                };
                float ac[128];
                uint32_t fr[3][8];
                uint64_t bd = (DB128 & ~0xFFFFFFFFull) | mkdesc(sb, DB128);
                reg_def<128>(ac);
                load(0);
                prep(0, fr[0]);
                PROFC(17);
#pragma unroll
                for (int s = 0; s < 14; s++) {
                    const uint32_t* f = fr[s % 3];
                    WAIT(B_FULL + g1_slot(s), s >= 7);
                    WG_FENCE();
                    wgmma_rl_256(ac, f[0], f[1], f[2], f[3], bd, s != 0);
                    wgmma_rl_256(ac, f[4], f[5], f[6], f[7], bd + 128, 1);
                    bd += s == 6 ? p.zero - 6 * 1024ull : 1024;
                    WG_COMMIT();
                    if (s < 13) prep(s + 1, fr[(s + 1) % 3]);
                    if (s > 0) { WG_WAIT(1); warp_arrive(BAR(B_EMPTY + g1_slot(s - 1))); }
                }
                fence_async_smem();
                PROFC(18);
                WG_WAIT(0);
                reg_fence<128>(ac);
                warp_arrive(BAR(B_EMPTY + 6));
#pragma unroll
                for (int g = 0; g < 16; g++) {
                    h2a[2 * g] = hmul2(pack2_relu(ac[4 * g], ac[4 * g + 1]), pack2(ac[64 + 4 * g], ac[64 + 4 * g + 1]));
                    h2a[2 * g + 1] = hmul2(pack2_relu(ac[4 * g + 2], ac[4 * g + 3]), pack2(ac[64 + 4 * g + 2], ac[64 + 4 * g + 3]));
                }
                bar_sync(1 + w, 128);
            } else reg_def<32>(h2a);
            PROFC(19);
            if (RUN(5)) {
                float ac[64];
                reg_def<64>(ac);
                const uint32_t bx = mkdesc(sb, dconst(8192, 1024, 1));
#pragma unroll kB
                for (int s = 0; s < 7; s++) {
                    WAIT(B_FULL + s, 0);
                    const uint32_t ad = a0 + s * 512, bd = bx + (slot_off(s) >> 4);
                    WG_FENCE();
#pragma unroll
                    for (int k = 0; k < 4; k++) wgmma_ss_128<DT, DB128>(ac, ad + k * 128, bd + k * 128, (s | k) != 0);
                    WG_COMMIT();
                    if (s == 1) {
#pragma unroll
                        for (int g = 0; g < 16; g++) { h2g[(fa / 8 + g) * 512] = h2a[2 * g]; h2g[(fa / 8 + g) * 512 + 32] = h2a[2 * g + 1]; }
                        warp_arrive(BAR(B_PUB + 6));
                    }
                    if (s > 0) { WG_WAIT(1); warp_arrive(BAR(B_EMPTY + s - 1)); }
                }
                WG_WAIT(0);
                reg_fence<64>(ac);
                warp_arrive(BAR(B_EMPTY + 6));
#pragma unroll
                for (int g = 0; g < 8; g++) {
                    h2b[2 * g] = hmul2(pack2_relu(ac[4 * g], ac[4 * g + 1]), pack2(ac[32 + 4 * g], ac[32 + 4 * g + 1]));
                    h2b[2 * g + 1] = hmul2(pack2_relu(ac[4 * g + 2], ac[4 * g + 3]), pack2(ac[32 + 4 * g + 2], ac[32 + 4 * g + 3]));
                }
            } else reg_def<16>(h2b);
            PROFC(27);
            if (RUN(6)) {
                float ac[32];
                reg_def<32>(ac);
                const uint32_t bx = mkdesc(sb, dconst(4096, 512, 2));
#pragma unroll kC
                for (int s = 0; s < 7; s++) {
                    WAIT(B_FULL + s, 1);
                    const uint32_t ad = a0 + s * 512, bd = bx + (slot_off(s) >> 4);
                    WG_FENCE();
#pragma unroll
                    for (int k = 0; k < 4; k++) wgmma_ss_64<DT, dconst(4096, 512, 2)>(ac, ad + k * 128, bd + k * 64, (s | k) != 0);
                    WG_COMMIT();
                    if (s == 1) {
#pragma unroll
                        for (int g = 0; g < 8; g++) { h2g[(fb / 8 + g) * 512] = h2b[2 * g]; h2g[(fb / 8 + g) * 512 + 32] = h2b[2 * g + 1]; }
                        warp_arrive(BAR(B_PUB + 7));
                    }
                    if (s > 0) { WG_WAIT(1); warp_arrive(BAR(B_EMPTY + s - 1)); }
                }
                WG_WAIT(0);
                reg_fence<32>(ac);
                __syncwarp();
                if (lane < 6) mbar_arrive(BAR(B_EMPTY + 6 + lane));
                PROFC(20);
#pragma unroll
                for (int g = 0; g < 4; g++) {
                    h2b[16 + 2 * g] = hmul2(pack2_relu(ac[4 * g], ac[4 * g + 1]), pack2(ac[16 + 4 * g], ac[16 + 4 * g + 1]));
                    h2b[16 + 2 * g + 1] = hmul2(pack2_relu(ac[4 * g + 2], ac[4 * g + 3]), pack2(ac[16 + 4 * g + 2], ac[16 + 4 * g + 3]));
                    h2g[(fc / 8 + g) * 512] = h2b[16 + 2 * g]; h2g[(fc / 8 + g) * 512 + 32] = h2b[16 + 2 * g + 1];
                }
                warp_arrive(BAR(B_PUB + 8));
                asm volatile("barrier.cluster.wait.aligned;" ::: "memory");
                if (lane == 0 && !sc) {
                    uint32_t rb;
                    asm volatile("mapa.shared::cluster.u32 %0, %1, %2;" : "=r"(rb) : "r"(BAR(B_PEER)), "r"(kh ^ 1));
                    asm volatile("mbarrier.arrive.relaxed.cluster.shared::cluster.b64 _, [%0];" ::"r"(rb) : "memory");
                }
            } else reg_def<8>(h2b + 16);
        }
        PROFC(21);
        if (RUN(7)) {
            float ac[56];
            reg_def<56>(ac);
            constexpr uint64_t DAN = dconst(2048, 128, 0);
            constexpr uint64_t DW = dconst(128, 512, 0);
            const uint32_t bx = mkdesc(sb, DW);
#pragma unroll
            for (int e = 0; e < 4; e++) {
                WAIT(B_FULL + e, 0);
                const uint64_t bd = ((DW & ~0xFFFFFFFFull) | bx) + (slot_off(e) >> 4);
                const uint32_t* hh = e < 2 ? h2a + 16 * e : h2b + 16 * (e - 2);
                WG_FENCE();
#pragma unroll
                for (int k = 0; k < (e < 3 ? 4 : 2); k++) wgmma_rl_112(ac, hh[4 * k], hh[4 * k + 1], hh[4 * k + 2], hh[4 * k + 3], bd + (k >> 1) * 512 + (k & 1) * 16, (e | k) != 0);
                WG_COMMIT();
                if (e > 0) { WG_WAIT(1); warp_arrive(BAR(B_EMPTY + e - 1)); }
            }
            PROFC(22);
            uint32_t ad = mkdesc(sb + 4 * 16384 + 8192 + w * 1024, DAN), bd = bx + 4 * 1024, fb_ = BAR(B_FULL + 4), eb_ = BAR(B_EMPTY + 3), par = sc;
#pragma unroll 1
            for (int e = 4; e < 25; e++) {
                mbar_wait_c(fb_, par);
                WG_FENCE();
                wgmma_ss_112<DAN, DW>(ac, ad, bd, 1);
                wgmma_ss_112<DAN, DW>(ac, ad + 256, bd + 16, 1);
                WG_COMMIT();
                WG_WAIT(1);
                warp_arrive(eb_);
                eb_ = fb_ + 8 * (B_EMPTY - B_FULL);
                ad += 1024; bd += 1024; fb_ += 8;
                if (e == 11 || e == 23) { ad -= 12 * 1024; bd -= 12 * 1024; fb_ -= 96; par = (par ^ 1) | sc; }
            }
            mbar_wait_cluster(BAR(B_PEER), sc);
            WG_WAIT(0);
            reg_fence<56>(ac);
            PROFC(24);
            uint32_t rdst, rbar;
            asm volatile("mapa.shared::cluster.u32 %0, %1, %2;" : "=r"(rdst) : "r"(sb + OFF_Y + (5 + w) * 16384 + t * 16), "r"(kh ^ 1 ^ sc));
            asm volatile("mapa.shared::cluster.u32 %0, %1, %2;" : "=r"(rbar) : "r"(BAR(B_XCH + w)), "r"(kh ^ 1 ^ sc));
#pragma unroll
            for (int g = 0; g < 7; g++) {
                const float v0 = ac[28 + 4 * g + 0], v1 = ac[28 + 4 * g + 1];
                const float v2 = ac[28 + 4 * g + 2], v3 = ac[28 + 4 * g + 3];
                if (!sc) asm volatile("st.async.shared::cluster.mbarrier::complete_tx::bytes.v4.f32 [%0], {%1,%2,%3,%4}, [%5];"
                             ::"r"(rdst + g * 2048), "f"(v0), "f"(v1), "f"(v2), "f"(v3), "r"(rbar) : "memory");
            }
            mbar_wait_cluster(BAR(B_XCH + w), sc);
            PROFC(25);
            uint32_t op[16];
#pragma unroll
            for (int g = 0; g < 7; g++) {
                const uint4 rv = *(const uint4*)(smem + OFF_Y + (5 + w) * 16384 + t * 16 + g * 2048);
                const float2 gb = *(const float2*)(smem + M_G + 224 + (8 * g + 2 * q) * 4);
                const float v0 = ac[4 * g + 0] + __uint_as_float(rv.x), v1 = ac[4 * g + 1] + __uint_as_float(rv.y);
                const float v2 = ac[4 * g + 2] + __uint_as_float(rv.z), v3 = ac[4 * g + 3] + __uint_as_float(rv.w);
                op[2 * g] = pack2(fmaf(gb.x, v0, bf_lo(x1p[2 * g])), fmaf(gb.y, v1, bf_hi(x1p[2 * g])));
                op[2 * g + 1] = pack2(fmaf(gb.x, v2, bf_lo(x1p[2 * g + 1])), fmaf(gb.y, v3, bf_hi(x1p[2 * g + 1])));
            }
            WAIT(B_EMPTY + 1, 0);
            const uint32_t oc = sb + OUT_STAGE + warp * 1792;
            const uint32_t oa = oc + (((lane >> 3) & 1) * 8 + (lane & 7)) * 112 + (lane >> 4) * 16;
            stsm4(oa, op[0], op[1], op[2], op[3]); stsm4(oa + 32, op[4], op[5], op[6], op[7]); stsm4(oa + 64, op[8], op[9], op[10], op[11]);
            asm volatile("stmatrix.sync.aligned.m8n8.x2.shared.b16 [%0], {%1,%2};" ::"r"(oa + 96), "r"(op[12]), "r"(op[13]));
            fence_async_smem();
            __syncwarp();
            asm volatile("{\n.reg .pred p;\nelect.sync _|p, 0xffffffff;\n@p cp.async.bulk.tensor.3d.global.shared::cta.bulk_group [%0, {%2, %3, %4}], [%1];\n"
                         "cp.async.bulk.commit_group;\ncp.async.bulk.wait_group.read 0;\n}" ::"l"(&p.om), "r"(oc), "r"(56 * j), "r"(128 * r + 16 * warp), "r"(0) : "memory");
        }
        PROFC(26);
        bar_sync(1 + w, 128);
        if (wi == 0) warp_arrive(BAR(B_DONE));
        return;
    }
    helper_late(p, r, j, warp PROF_ARGS);
}

#undef act
typedef CUresult (*EncodeFn)(CUtensorMap*, CUtensorMapDataType, cuuint32_t, void*, const cuuint64_t*, const cuuint64_t*, const cuuint32_t*,
                             const cuuint32_t*, CUtensorMapInterleave, CUtensorMapSwizzle, CUtensorMapL2promotion, CUtensorMapFloatOOBfill);

static void make_map(EncodeFn fn, CUtensorMap* m, const void* ptr, uint64_t d0, uint64_t d1, uint64_t d2, uint64_t s1, uint64_t s2,
                     uint32_t b0, uint32_t b1, uint32_t b2, CUtensorMapSwizzle sw) {
    cuuint64_t dims[3] = {d0, d1, d2}, strides[2] = {s1, s2};
    cuuint32_t box[3] = {b0, b1, b2}, es[3] = {1, 1, 1};
    CUresult rc = fn(m, CU_TENSOR_MAP_DATA_TYPE_BFLOAT16, 3, (void*)ptr, dims, strides, box, es, CU_TENSOR_MAP_INTERLEAVE_NONE, sw,
                     CU_TENSOR_MAP_L2_PROMOTION_L2_128B, CU_TENSOR_MAP_FLOAT_OOB_FILL_NONE);
    (void)rc;
}

extern "C" void kernel_launch(void* const* d_in, const int* in_sizes, int n_in, void* d_out, int out_size) {
    (void)in_sizes; (void)n_in; (void)out_size;
    static EncodeFn fn = nullptr;
    static uint32_t* act_base = nullptr;
    if (!fn) {
        cudaDriverEntryPointQueryResult st;
        cudaGetDriverEntryPoint("cuTensorMapEncodeTiled", (void**)&fn, cudaEnableDefault, &st);
        void* a = nullptr;
        cudaGetSymbolAddress(&a, g_act);
        act_base = (uint32_t*)(((uintptr_t)a + 0xFFFFF) & ~(uintptr_t)0xFFFFF);
        cudaFuncSetAttribute(fused_block_kernel, cudaFuncAttributeMaxDynamicSharedMemorySize, SMEM_BYTES);
    }
    Params p;
    p.x = (const bf16*)d_in[0];
    const bf16* wqkv = (const bf16*)d_in[1];
    p.wqkv = wqkv;
    p.wop = (const bf16*)d_in[2];
    p.wg = (const bf16*)d_in[4];
    p.wu = (const bf16*)d_in[5];
    p.wd = (const bf16*)d_in[6];
    p.c = (const bf16*)d_in[7];
    p.wmod = (const bf16*)d_in[8];
    p.out = (bf16*)d_out;
    p.zero = 0;
    p.actb = act_base;
    make_map(fn, &p.wm, p.wmod, 2688, 448, 1, 5376, 5376 * 448, 16, 224, 1, CU_TENSOR_MAP_SWIZZLE_NONE);
    make_map(fn, &p.wm2, p.wmod, 2688, 448, 1, 5376, 5376 * 448, 32, 224, 1, CU_TENSOR_MAP_SWIZZLE_NONE);
    make_map(fn, &p.om, p.out, 448, 2048, 1, 896, 896 * 2048, 56, 16, 1, CU_TENSOR_MAP_SWIZZLE_NONE);
    make_map(fn, &p.xm, p.x, 448, 2048, 1, 896, 896 * 2048, 64, 128, 1, CU_TENSOR_MAP_SWIZZLE_128B);
    make_map(fn, &p.qkv, wqkv, 1344, 448, 1, 2688, 2688 * 448, 64, 224, 1, CU_TENSOR_MAP_SWIZZLE_128B);
    make_map(fn, &p.wo, p.wop, 448, 448, 1, 896, 896 * 448, 64, 224, 1, CU_TENSOR_MAP_SWIZZLE_128B);
    make_map(fn, &p.ga, p.wg, 64, 448, 28, 3584, 128, 64, 32, 2, CU_TENSOR_MAP_SWIZZLE_128B);
    make_map(fn, &p.ua, p.wu, 64, 448, 28, 3584, 128, 64, 32, 2, CU_TENSOR_MAP_SWIZZLE_128B);
    make_map(fn, &p.gb, p.wg, 64, 448, 28, 3584, 128, 64, 64, 1, CU_TENSOR_MAP_SWIZZLE_128B);
    make_map(fn, &p.ub, p.wu, 64, 448, 28, 3584, 128, 64, 64, 1, CU_TENSOR_MAP_SWIZZLE_128B);
    make_map(fn, &p.gc, p.wg, 32, 448, 56, 3584, 64, 32, 64, 1, CU_TENSOR_MAP_SWIZZLE_64B);
    make_map(fn, &p.uc, p.wu, 32, 448, 56, 3584, 64, 32, 64, 1, CU_TENSOR_MAP_SWIZZLE_64B);
    make_map(fn, &p.dn, p.wd, 8, 1792, 56, 896, 16, 8, 32, 7, CU_TENSOR_MAP_SWIZZLE_NONE);
    fused_block_kernel<<<GRID, 384, SMEM_BYTES>>>(p);
}
```

```cpp
#include <cuda_runtime.h>
#include <cuda_bf16.h>
#include <cuda.h>
#include <stdint.h>

typedef __nv_bfloat16 bf16;

template<uint64_t CA, uint64_t CB> __device__ __forceinline__ void wgmma_sk_160(float* d, uint32_t da, uint32_t db, int sd) {
  asm volatile("{\n.reg .pred p;\n.reg .b64 a, b;\nsetp.ne.b32 p, %82, 0;\nmov.b64 a, {%80, %83};\nmov.b64 b, {%81, %84};\n"
    "wgmma.mma_async.sync.aligned.m64n160k16.f32.bf16.bf16 {%0,%1,%2,%3,%4,%5,%6,%7,%8,%9,%10,%11,%12,%13,%14,%15,%16,%17,%18,%19,%20,%21,%22,%23,%24,%25,%26,%27,%28,%29,%30,%31,%32,%33,%34,%35,%36,%37,%38,%39,%40,%41,%42,%43,%44,%45,%46,%47,%48,%49,%50,%51,%52,%53,%54,%55,%56,%57,%58,%59,%60,%61,%62,%63,%64,%65,%66,%67,%68,%69,%70,%71,%72,%73,%74,%75,%76,%77,%78,%79}, a, b, p, 1, 1, 0, 0;\n}\n"
    : "+f"(d[0]),"+f"(d[1]),"+f"(d[2]),"+f"(d[3]),"+f"(d[4]),"+f"(d[5]),"+f"(d[6]),"+f"(d[7]),"+f"(d[8]),"+f"(d[9]),"+f"(d[10]),"+f"(d[11]),"+f"(d[12]),"+f"(d[13]),"+f"(d[14]),"+f"(d[15]),"+f"(d[16]),"+f"(d[17]),"+f"(d[18]),"+f"(d[19]),"+f"(d[20]),"+f"(d[21]),"+f"(d[22]),"+f"(d[23]),"+f"(d[24]),"+f"(d[25]),"+f"(d[26]),"+f"(d[27]),"+f"(d[28]),"+f"(d[29]),"+f"(d[30]),"+f"(d[31]),"+f"(d[32]),"+f"(d[33]),"+f"(d[34]),"+f"(d[35]),"+f"(d[36]),"+f"(d[37]),"+f"(d[38]),"+f"(d[39]),"+f"(d[40]),"+f"(d[41]),"+f"(d[42]),"+f"(d[43]),"+f"(d[44]),"+f"(d[45]),"+f"(d[46]),"+f"(d[47]),"+f"(d[48]),"+f"(d[49]),"+f"(d[50]),"+f"(d[51]),"+f"(d[52]),"+f"(d[53]),"+f"(d[54]),"+f"(d[55]),"+f"(d[56]),"+f"(d[57]),"+f"(d[58]),"+f"(d[59]),"+f"(d[60]),"+f"(d[61]),"+f"(d[62]),"+f"(d[63]),"+f"(d[64]),"+f"(d[65]),"+f"(d[66]),"+f"(d[67]),"+f"(d[68]),"+f"(d[69]),"+f"(d[70]),"+f"(d[71]),"+f"(d[72]),"+f"(d[73]),"+f"(d[74]),"+f"(d[75]),"+f"(d[76]),"+f"(d[77]),"+f"(d[78]),"+f"(d[79])
    : "r"(da), "r"(db), "r"(sd), "n"((uint32_t)(CA >> 32)), "n"((uint32_t)(CB >> 32)));
}
__device__ __forceinline__ void wgmma_rl_56(float* d, uint32_t a0, uint32_t a1, uint32_t a2, uint32_t a3, uint64_t db, int sd) {
  asm volatile("{\n.reg .pred p;\nsetp.ne.b32 p, %33, 0;\n"
    "wgmma.mma_async.sync.aligned.m64n56k16.f32.bf16.bf16 {%0,%1,%2,%3,%4,%5,%6,%7,%8,%9,%10,%11,%12,%13,%14,%15,%16,%17,%18,%19,%20,%21,%22,%23,%24,%25,%26,%27}, {%28,%29,%30,%31}, %32, p, 1, 1, 1;\n}\n"
    : "+f"(d[0]),"+f"(d[1]),"+f"(d[2]),"+f"(d[3]),"+f"(d[4]),"+f"(d[5]),"+f"(d[6]),"+f"(d[7]),"+f"(d[8]),"+f"(d[9]),"+f"(d[10]),"+f"(d[11]),"+f"(d[12]),"+f"(d[13]),"+f"(d[14]),"+f"(d[15]),"+f"(d[16]),"+f"(d[17]),"+f"(d[18]),"+f"(d[19]),"+f"(d[20]),"+f"(d[21]),"+f"(d[22]),"+f"(d[23]),"+f"(d[24]),"+f"(d[25]),"+f"(d[26]),"+f"(d[27])
    : "r"(a0), "r"(a1), "r"(a2), "r"(a3), "l"(db), "r"(sd));
}
template<uint64_t CA, uint64_t CB> __device__ __forceinline__ void wgmma_ss_56(float* d, uint32_t da, uint32_t db, int sd) {
  asm volatile("{\n.reg .pred p;\n.reg .b64 a, b;\nsetp.ne.b32 p, %30, 0;\nmov.b64 a, {%28, %31};\nmov.b64 b, {%29, %32};\n"
    "wgmma.mma_async.sync.aligned.m64n56k16.f32.bf16.bf16 {%0,%1,%2,%3,%4,%5,%6,%7,%8,%9,%10,%11,%12,%13,%14,%15,%16,%17,%18,%19,%20,%21,%22,%23,%24,%25,%26,%27}, a, b, p, 1, 1, 0, 1;\n}\n"
    : "+f"(d[0]),"+f"(d[1]),"+f"(d[2]),"+f"(d[3]),"+f"(d[4]),"+f"(d[5]),"+f"(d[6]),"+f"(d[7]),"+f"(d[8]),"+f"(d[9]),"+f"(d[10]),"+f"(d[11]),"+f"(d[12]),"+f"(d[13]),"+f"(d[14]),"+f"(d[15]),"+f"(d[16]),"+f"(d[17]),"+f"(d[18]),"+f"(d[19]),"+f"(d[20]),"+f"(d[21]),"+f"(d[22]),"+f"(d[23]),"+f"(d[24]),"+f"(d[25]),"+f"(d[26]),"+f"(d[27])
    : "r"(da), "r"(db), "r"(sd), "n"((uint32_t)(CA >> 32)), "n"((uint32_t)(CB >> 32)));
}
__device__ __forceinline__ void wgmma_rl_256(float* d, uint32_t a0, uint32_t a1, uint32_t a2, uint32_t a3, uint64_t db, int sd) {
  asm volatile("{\n.reg .pred p;\nsetp.ne.b32 p, %133, 0;\n"
    "wgmma.mma_async.sync.aligned.m64n256k16.f32.bf16.bf16 {%0,%1,%2,%3,%4,%5,%6,%7,%8,%9,%10,%11,%12,%13,%14,%15,%16,%17,%18,%19,%20,%21,%22,%23,%24,%25,%26,%27,%28,%29,%30,%31,%32,%33,%34,%35,%36,%37,%38,%39,%40,%41,%42,%43,%44,%45,%46,%47,%48,%49,%50,%51,%52,%53,%54,%55,%56,%57,%58,%59,%60,%61,%62,%63,%64,%65,%66,%67,%68,%69,%70,%71,%72,%73,%74,%75,%76,%77,%78,%79,%80,%81,%82,%83,%84,%85,%86,%87,%88,%89,%90,%91,%92,%93,%94,%95,%96,%97,%98,%99,%100,%101,%102,%103,%104,%105,%106,%107,%108,%109,%110,%111,%112,%113,%114,%115,%116,%117,%118,%119,%120,%121,%122,%123,%124,%125,%126,%127}, {%128,%129,%130,%131}, %132, p, 1, 1, 1;\n}\n"
    : "+f"(d[0]),"+f"(d[1]),"+f"(d[2]),"+f"(d[3]),"+f"(d[4]),"+f"(d[5]),"+f"(d[6]),"+f"(d[7]),"+f"(d[8]),"+f"(d[9]),"+f"(d[10]),"+f"(d[11]),"+f"(d[12]),"+f"(d[13]),"+f"(d[14]),"+f"(d[15]),"+f"(d[16]),"+f"(d[17]),"+f"(d[18]),"+f"(d[19]),"+f"(d[20]),"+f"(d[21]),"+f"(d[22]),"+f"(d[23]),"+f"(d[24]),"+f"(d[25]),"+f"(d[26]),"+f"(d[27]),"+f"(d[28]),"+f"(d[29]),"+f"(d[30]),"+f"(d[31]),"+f"(d[32]),"+f"(d[33]),"+f"(d[34]),"+f"(d[35]),"+f"(d[36]),"+f"(d[37]),"+f"(d[38]),"+f"(d[39]),"+f"(d[40]),"+f"(d[41]),"+f"(d[42]),"+f"(d[43]),"+f"(d[44]),"+f"(d[45]),"+f"(d[46]),"+f"(d[47]),"+f"(d[48]),"+f"(d[49]),"+f"(d[50]),"+f"(d[51]),"+f"(d[52]),"+f"(d[53]),"+f"(d[54]),"+f"(d[55]),"+f"(d[56]),"+f"(d[57]),"+f"(d[58]),"+f"(d[59]),"+f"(d[60]),"+f"(d[61]),"+f"(d[62]),"+f"(d[63]),"+f"(d[64]),"+f"(d[65]),"+f"(d[66]),"+f"(d[67]),"+f"(d[68]),"+f"(d[69]),"+f"(d[70]),"+f"(d[71]),"+f"(d[72]),"+f"(d[73]),"+f"(d[74]),"+f"(d[75]),"+f"(d[76]),"+f"(d[77]),"+f"(d[78]),"+f"(d[79]),"+f"(d[80]),"+f"(d[81]),"+f"(d[82]),"+f"(d[83]),"+f"(d[84]),"+f"(d[85]),"+f"(d[86]),"+f"(d[87]),"+f"(d[88]),"+f"(d[89]),"+f"(d[90]),"+f"(d[91]),"+f"(d[92]),"+f"(d[93]),"+f"(d[94]),"+f"(d[95]),"+f"(d[96]),"+f"(d[97]),"+f"(d[98]),"+f"(d[99]),"+f"(d[100]),"+f"(d[101]),"+f"(d[102]),"+f"(d[103]),"+f"(d[104]),"+f"(d[105]),"+f"(d[106]),"+f"(d[107]),"+f"(d[108]),"+f"(d[109]),"+f"(d[110]),"+f"(d[111]),"+f"(d[112]),"+f"(d[113]),"+f"(d[114]),"+f"(d[115]),"+f"(d[116]),"+f"(d[117]),"+f"(d[118]),"+f"(d[119]),"+f"(d[120]),"+f"(d[121]),"+f"(d[122]),"+f"(d[123]),"+f"(d[124]),"+f"(d[125]),"+f"(d[126]),"+f"(d[127])
    : "r"(a0), "r"(a1), "r"(a2), "r"(a3), "l"(db), "r"(sd));
}
template<uint64_t CA, uint64_t CB> __device__ __forceinline__ void wgmma_ss_128(float* d, uint32_t da, uint32_t db, int sd) {
  asm volatile("{\n.reg .pred p;\n.reg .b64 a, b;\nsetp.ne.b32 p, %66, 0;\nmov.b64 a, {%64, %67};\nmov.b64 b, {%65, %68};\n"
    "wgmma.mma_async.sync.aligned.m64n128k16.f32.bf16.bf16 {%0,%1,%2,%3,%4,%5,%6,%7,%8,%9,%10,%11,%12,%13,%14,%15,%16,%17,%18,%19,%20,%21,%22,%23,%24,%25,%26,%27,%28,%29,%30,%31,%32,%33,%34,%35,%36,%37,%38,%39,%40,%41,%42,%43,%44,%45,%46,%47,%48,%49,%50,%51,%52,%53,%54,%55,%56,%57,%58,%59,%60,%61,%62,%63}, a, b, p, 1, 1, 0, 1;\n}\n"
    : "+f"(d[0]),"+f"(d[1]),"+f"(d[2]),"+f"(d[3]),"+f"(d[4]),"+f"(d[5]),"+f"(d[6]),"+f"(d[7]),"+f"(d[8]),"+f"(d[9]),"+f"(d[10]),"+f"(d[11]),"+f"(d[12]),"+f"(d[13]),"+f"(d[14]),"+f"(d[15]),"+f"(d[16]),"+f"(d[17]),"+f"(d[18]),"+f"(d[19]),"+f"(d[20]),"+f"(d[21]),"+f"(d[22]),"+f"(d[23]),"+f"(d[24]),"+f"(d[25]),"+f"(d[26]),"+f"(d[27]),"+f"(d[28]),"+f"(d[29]),"+f"(d[30]),"+f"(d[31]),"+f"(d[32]),"+f"(d[33]),"+f"(d[34]),"+f"(d[35]),"+f"(d[36]),"+f"(d[37]),"+f"(d[38]),"+f"(d[39]),"+f"(d[40]),"+f"(d[41]),"+f"(d[42]),"+f"(d[43]),"+f"(d[44]),"+f"(d[45]),"+f"(d[46]),"+f"(d[47]),"+f"(d[48]),"+f"(d[49]),"+f"(d[50]),"+f"(d[51]),"+f"(d[52]),"+f"(d[53]),"+f"(d[54]),"+f"(d[55]),"+f"(d[56]),"+f"(d[57]),"+f"(d[58]),"+f"(d[59]),"+f"(d[60]),"+f"(d[61]),"+f"(d[62]),"+f"(d[63])
    : "r"(da), "r"(db), "r"(sd), "n"((uint32_t)(CA >> 32)), "n"((uint32_t)(CB >> 32)));
}
template<uint64_t CA, uint64_t CB> __device__ __forceinline__ void wgmma_ss_64(float* d, uint32_t da, uint32_t db, int sd) {
  asm volatile("{\n.reg .pred p;\n.reg .b64 a, b;\nsetp.ne.b32 p, %34, 0;\nmov.b64 a, {%32, %35};\nmov.b64 b, {%33, %36};\n"
    "wgmma.mma_async.sync.aligned.m64n64k16.f32.bf16.bf16 {%0,%1,%2,%3,%4,%5,%6,%7,%8,%9,%10,%11,%12,%13,%14,%15,%16,%17,%18,%19,%20,%21,%22,%23,%24,%25,%26,%27,%28,%29,%30,%31}, a, b, p, 1, 1, 0, 1;\n}\n"
    : "+f"(d[0]),"+f"(d[1]),"+f"(d[2]),"+f"(d[3]),"+f"(d[4]),"+f"(d[5]),"+f"(d[6]),"+f"(d[7]),"+f"(d[8]),"+f"(d[9]),"+f"(d[10]),"+f"(d[11]),"+f"(d[12]),"+f"(d[13]),"+f"(d[14]),"+f"(d[15]),"+f"(d[16]),"+f"(d[17]),"+f"(d[18]),"+f"(d[19]),"+f"(d[20]),"+f"(d[21]),"+f"(d[22]),"+f"(d[23]),"+f"(d[24]),"+f"(d[25]),"+f"(d[26]),"+f"(d[27]),"+f"(d[28]),"+f"(d[29]),"+f"(d[30]),"+f"(d[31])
    : "r"(da), "r"(db), "r"(sd), "n"((uint32_t)(CA >> 32)), "n"((uint32_t)(CB >> 32)));
}
template<uint64_t CA, uint64_t CB> __device__ __forceinline__ void wgmma_ss_112(float* d, uint32_t da, uint32_t db, int sd) {
  asm volatile("{\n.reg .pred p;\n.reg .b64 a, b;\nsetp.ne.b32 p, %58, 0;\nmov.b64 a, {%56, %59};\nmov.b64 b, {%57, %60};\n"
    "wgmma.mma_async.sync.aligned.m64n112k16.f32.bf16.bf16 {%0,%1,%2,%3,%4,%5,%6,%7,%8,%9,%10,%11,%12,%13,%14,%15,%16,%17,%18,%19,%20,%21,%22,%23,%24,%25,%26,%27,%28,%29,%30,%31,%32,%33,%34,%35,%36,%37,%38,%39,%40,%41,%42,%43,%44,%45,%46,%47,%48,%49,%50,%51,%52,%53,%54,%55}, a, b, p, 1, 1, 0, 1;\n}\n"
    : "+f"(d[0]),"+f"(d[1]),"+f"(d[2]),"+f"(d[3]),"+f"(d[4]),"+f"(d[5]),"+f"(d[6]),"+f"(d[7]),"+f"(d[8]),"+f"(d[9]),"+f"(d[10]),"+f"(d[11]),"+f"(d[12]),"+f"(d[13]),"+f"(d[14]),"+f"(d[15]),"+f"(d[16]),"+f"(d[17]),"+f"(d[18]),"+f"(d[19]),"+f"(d[20]),"+f"(d[21]),"+f"(d[22]),"+f"(d[23]),"+f"(d[24]),"+f"(d[25]),"+f"(d[26]),"+f"(d[27]),"+f"(d[28]),"+f"(d[29]),"+f"(d[30]),"+f"(d[31]),"+f"(d[32]),"+f"(d[33]),"+f"(d[34]),"+f"(d[35]),"+f"(d[36]),"+f"(d[37]),"+f"(d[38]),"+f"(d[39]),"+f"(d[40]),"+f"(d[41]),"+f"(d[42]),"+f"(d[43]),"+f"(d[44]),"+f"(d[45]),"+f"(d[46]),"+f"(d[47]),"+f"(d[48]),"+f"(d[49]),"+f"(d[50]),"+f"(d[51]),"+f"(d[52]),"+f"(d[53]),"+f"(d[54]),"+f"(d[55])
    : "r"(da), "r"(db), "r"(sd), "n"((uint32_t)(CA >> 32)), "n"((uint32_t)(CB >> 32)));
}
__device__ __forceinline__ void wgmma_rl_112(float* d, uint32_t a0, uint32_t a1, uint32_t a2, uint32_t a3, uint64_t db, int sd) {
  asm volatile("{\n.reg .pred p;\nsetp.ne.b32 p, %61, 0;\n"
    "wgmma.mma_async.sync.aligned.m64n112k16.f32.bf16.bf16 {%0,%1,%2,%3,%4,%5,%6,%7,%8,%9,%10,%11,%12,%13,%14,%15,%16,%17,%18,%19,%20,%21,%22,%23,%24,%25,%26,%27,%28,%29,%30,%31,%32,%33,%34,%35,%36,%37,%38,%39,%40,%41,%42,%43,%44,%45,%46,%47,%48,%49,%50,%51,%52,%53,%54,%55}, {%56,%57,%58,%59}, %60, p, 1, 1, 1;\n}\n"
    : "+f"(d[0]),"+f"(d[1]),"+f"(d[2]),"+f"(d[3]),"+f"(d[4]),"+f"(d[5]),"+f"(d[6]),"+f"(d[7]),"+f"(d[8]),"+f"(d[9]),"+f"(d[10]),"+f"(d[11]),"+f"(d[12]),"+f"(d[13]),"+f"(d[14]),"+f"(d[15]),"+f"(d[16]),"+f"(d[17]),"+f"(d[18]),"+f"(d[19]),"+f"(d[20]),"+f"(d[21]),"+f"(d[22]),"+f"(d[23]),"+f"(d[24]),"+f"(d[25]),"+f"(d[26]),"+f"(d[27]),"+f"(d[28]),"+f"(d[29]),"+f"(d[30]),"+f"(d[31]),"+f"(d[32]),"+f"(d[33]),"+f"(d[34]),"+f"(d[35]),"+f"(d[36]),"+f"(d[37]),"+f"(d[38]),"+f"(d[39]),"+f"(d[40]),"+f"(d[41]),"+f"(d[42]),"+f"(d[43]),"+f"(d[44]),"+f"(d[45]),"+f"(d[46]),"+f"(d[47]),"+f"(d[48]),"+f"(d[49]),"+f"(d[50]),"+f"(d[51]),"+f"(d[52]),"+f"(d[53]),"+f"(d[54]),"+f"(d[55])
    : "r"(a0), "r"(a1), "r"(a2), "r"(a3), "l"(db), "r"(sd));
}

constexpr int DM = 448;
constexpr int NCTA = 128;
#define MAPPING 1
#define GRID 128
#define PINGPONG 0
#define WIN 6
#define WIN_END 25
#define UNR_B 1
#define UNR_C 1
constexpr int kB = UNR_B, kC = UNR_C;
#define LIKELY(x) __builtin_expect(!!(x), 1)
#define PACE 1
#define PACE_END 6
#define GEMV_AT 0
#define NPRE 14
#define ATT_OFF 0
#define ATT_WG 1
#define XFIRST 7
#define KDELAY 0
#define KEARLY 1
#define VPRE 3
#define VGATE 2
#define LNMODE 0
#define MAP_S 4
constexpr int SPIN_LIMIT = 1 << 22;

constexpr uint32_t OFF_X = 0, OFF_Y = 114688, OFF_MISC = 229376, SMEM_BYTES = 232448;
constexpr uint32_t Y_VR = 0, Y_K = 28672, Y_KOWN = 57344, Y_VOWN = 71680, Y_Q = 86016;
constexpr uint32_t HALF = 57344;
constexpr uint32_t X_STAT = 49152;
constexpr uint32_t OUT_STAGE = 16384;
constexpr uint32_t M_BAR = OFF_MISC;
constexpr uint32_t M_ST = OFF_MISC + 512;
constexpr uint32_t M_G = OFF_MISC + 2304;
constexpr uint32_t M_EPOCH = OFF_MISC + 3040;
enum { B_XFULL = 0, B_FULLK = 7, B_FULLV = 8, B_FULLQ, B_KRFULL, B_VRFULL, B_WOFULL, B_XCH, B_MOD1 = 15, B_FULL = 16, B_WMFULL = 30,
       B_EMPTY = 32, B_XFREE = B_EMPTY + 12, B_GEMV, B_PEER,
       B_PUB = 47,
       B_WMFREE = 56, B_HRDY, B_GFULL = B_HRDY + 3, B_DONE = 31, B_DUMMY = B_GEMV };

__device__ uint32_t g_ticket;
__device__ __align__(128) uint32_t g_mod[8 * 6 * DM];
__device__ __align__(128) uint32_t g_flag[144 * 128];
constexpr int RB_WORDS = 262144, RB_KV = 0, RB_O = 57344, RB_X1 = 86016, RB_H2 = 143360, RB_ST = 258048;
__device__ __align__(128) uint32_t g_act[18 * RB_WORDS];
__device__ __align__(128) uint32_t g_wd[56 * 4 * 1792];
#define PROFH(id)
#define PROFH1(id)
#define PROFC(id)

struct alignas(64) Params {
    CUtensorMap wm, wm2, om, xm, qkv, wo, ga, ua, gb, ub, gc, uc, dn;
    const bf16 *x, *c, *wqkv, *wmod, *wg, *wu, *wd, *wop;
    bf16* out;
    uint32_t* actb;
    uint32_t zero;
};

__device__ __forceinline__ void mbar_init(uint32_t bar, int cnt) { asm volatile("mbarrier.init.shared::cta.b64 [%0], %1;" ::"r"(bar), "r"(cnt) : "memory"); }
__device__ __forceinline__ void mbar_expect_tx(uint32_t bar, uint32_t bytes) { asm volatile("mbarrier.arrive.expect_tx.shared::cta.b64 _, [%0], %1;" ::"r"(bar), "r"(bytes) : "memory"); }
__device__ __forceinline__ void mbar_arrive(uint32_t bar) { asm volatile("mbarrier.arrive.shared::cta.b64 _, [%0];" ::"r"(bar) : "memory"); }
__device__ __forceinline__ void mbar_wait(uint32_t bar, uint32_t parity) {
    uint32_t ok; int n = 0;
    do {
        asm volatile("{\n.reg .pred p;\nmbarrier.try_wait.parity.shared::cta.b64 p, [%1], %2;\nselp.u32 %0, 1, 0, p;\n}" : "=r"(ok) : "r"(bar), "r"(parity) : "memory");
        if (++n > SPIN_LIMIT) __trap();
    } while (!ok);
}
__device__ __forceinline__ void mbar_wait_c(uint32_t bar, uint32_t parity) {
    asm volatile("{\n.reg .pred p;\nWL:\nmbarrier.try_wait.parity.shared::cta.b64 p, [%0], %1, 0x989680;\n@!p bra WL;\n}" ::"r"(bar), "r"(parity) : "memory");
}
__device__ __forceinline__ void mbar_wait_cluster(uint32_t bar, uint32_t parity) {
    asm volatile("{\n.reg .pred p;\nWL:\nmbarrier.try_wait.parity.acquire.cluster.shared::cta.b64 p, [%0], %1, 0x989680;\n@!p bra WL;\n}" ::"r"(bar), "r"(parity) : "memory");
}
__device__ __forceinline__ void warp_arrive(uint32_t bar) {
    __syncwarp();
    asm volatile("{\n.reg .pred p;\nelect.sync _|p, 0xffffffff;\n@p mbarrier.arrive.shared::cta.b64 _, [%0];\n}" ::"r"(bar) : "memory");
}
__device__ __forceinline__ int opaque(int v) { return __shfl_sync(~0u, v, 0); }
__device__ __forceinline__ int fresh_tid() { int v; asm volatile("mov.u32 %0, %%tid.x;" : "=r"(v)); return v; }
__device__ __forceinline__ void bar_sync(int id, int n) { asm volatile("bar.sync %0, %1;" ::"r"(id), "r"(n) : "memory"); }
__device__ __forceinline__ void bar_arrive(int id, int n) { asm volatile("bar.arrive %0, %1;" ::"r"(id), "r"(n) : "memory"); }
__device__ __forceinline__ void fence_async_smem() { asm volatile("fence.proxy.async.shared::cta;" ::: "memory"); }
__device__ __forceinline__ void fence_async_global() { asm volatile("fence.proxy.async.global;" ::: "memory"); }
__device__ __forceinline__ void fence_gpu() { asm volatile("fence.release.gpu;" ::: "memory"); }
__device__ __forceinline__ void tma3(uint32_t dst, const CUtensorMap* m, int c0, int c1, int c2, uint32_t bar) {
    asm volatile("cp.async.bulk.tensor.3d.shared::cluster.global.mbarrier::complete_tx::bytes [%0], [%1, {%3, %4, %5}], [%2];"
                 ::"r"(dst), "l"(m), "r"(bar), "r"(c0), "r"(c1), "r"(c2) : "memory");
}
__device__ __forceinline__ void bulk_load(uint32_t dst, const void* src, uint32_t bytes, uint32_t bar) {
    asm volatile("cp.async.bulk.shared::cluster.global.mbarrier::complete_tx::bytes [%0], [%1], %2, [%3];" ::"r"(dst), "l"(src), "r"(bytes), "r"(bar) : "memory");
}
__device__ __forceinline__ void expect_e(uint32_t bar, uint32_t bytes) {
    asm volatile("{\n.reg .pred p;\nelect.sync _|p, 0xffffffff;\n@p mbarrier.arrive.expect_tx.shared::cta.b64 _, [%0], %1;\n}" ::"r"(bar), "r"(bytes) : "memory");
}
__device__ __forceinline__ void tma3_e(uint32_t dst, const CUtensorMap* m, int c0, int c1, int c2, uint32_t bar) {
    asm volatile("{\n.reg .pred p;\nelect.sync _|p, 0xffffffff;\n@p cp.async.bulk.tensor.3d.shared::cluster.global.mbarrier::complete_tx::bytes [%0], [%1, {%3, %4, %5}], [%2];\n}"
                 ::"r"(dst), "l"(m), "r"(bar), "r"(c0), "r"(c1), "r"(c2) : "memory");
}
__device__ __forceinline__ void bulk_e(uint32_t dst, const void* src, uint32_t bytes, uint32_t bar) {
    asm volatile("{\n.reg .pred p;\nelect.sync _|p, 0xffffffff;\n@p cp.async.bulk.shared::cluster.global.mbarrier::complete_tx::bytes [%0], [%1], %2, [%3];\n}"
                 ::"r"(dst), "l"(src), "r"(bytes), "r"(bar) : "memory");
}
__device__ __forceinline__ void init_e(uint32_t bar, int cnt) {
    asm volatile("{\n.reg .pred p;\nelect.sync _|p, 0xffffffff;\n@p mbarrier.init.shared::cta.b64 [%0], %1;\n}" ::"r"(bar), "r"(cnt) : "memory");
}
__device__ __forceinline__ void l2_prefetch_e(const void* src, uint32_t bytes) {
    asm volatile("{\n.reg .pred p;\nelect.sync _|p, 0xffffffff;\n@p cp.async.bulk.prefetch.L2.global [%0], %1;\n}" ::"l"(src), "r"(bytes) : "memory");
}
__device__ __forceinline__ uint32_t ld_relaxed(const uint32_t* p) { uint32_t v; asm volatile("ld.relaxed.gpu.global.u32 %0, [%1];" : "=r"(v) : "l"(p) : "memory"); return v; }
__device__ __forceinline__ void st_relaxed(uint32_t* p, uint32_t v) { asm volatile("st.relaxed.gpu.global.u32 [%0], %1;" ::"l"(p), "r"(v) : "memory"); }
__device__ __forceinline__ uint4 ld_relaxed4(const uint4* p) { uint4 v; asm volatile("ld.relaxed.gpu.global.v4.u32 {%0,%1,%2,%3}, [%4];" : "=r"(v.x), "=r"(v.y), "=r"(v.z), "=r"(v.w) : "l"(p) : "memory"); return v; }
__device__ __forceinline__ void st_relaxed4(uint4* p, uint4 v) { asm volatile("st.relaxed.gpu.global.v4.u32 [%0], {%1,%2,%3,%4};" ::"l"(p), "r"(v.x), "r"(v.y), "r"(v.z), "r"(v.w) : "memory"); }
__device__ __forceinline__ uint4 ldg_nc4(const void* p) { uint4 v; asm volatile("ld.global.nc.L1::no_allocate.v4.u32 {%0,%1,%2,%3}, [%4];" : "=r"(v.x), "=r"(v.y), "=r"(v.z), "=r"(v.w) : "l"(p)); return v; }
__device__ __forceinline__ uint32_t ldg_nc(const void* p) { uint32_t v; asm volatile("ld.global.nc.u32 %0, [%1];" : "=r"(v) : "l"(p)); return v; }
__device__ __forceinline__ uint32_t ld_acquire(const uint32_t* p) { uint32_t v; asm volatile("ld.acquire.gpu.global.u32 %0, [%1];" : "=r"(v) : "l"(p) : "memory"); return v; }
__device__ __forceinline__ uint4 lds4(uint32_t a) { uint4 v; asm volatile("ld.shared.v4.u32 {%0,%1,%2,%3}, [%4];" : "=r"(v.x), "=r"(v.y), "=r"(v.z), "=r"(v.w) : "r"(a) : "memory"); return v; }
__device__ __forceinline__ float2 lds2f(uint32_t a) { float2 v; asm volatile("ld.shared.v2.f32 {%0,%1}, [%2];" : "=f"(v.x), "=f"(v.y) : "r"(a) : "memory"); return v; }
__device__ __forceinline__ uint32_t lds1(uint32_t a) { uint32_t v; asm volatile("ld.shared.u32 %0, [%1];" : "=r"(v) : "r"(a) : "memory"); return v; }
__device__ __forceinline__ void sts4(uint32_t a, uint4 v) { asm volatile("st.shared.v4.u32 [%0], {%1,%2,%3,%4};" ::"r"(a), "r"(v.x), "r"(v.y), "r"(v.z), "r"(v.w) : "memory"); }
__device__ __forceinline__ void sts2(uint32_t a, uint32_t x, uint32_t y) { asm volatile("st.shared.v2.u32 [%0], {%1,%2};" ::"r"(a), "r"(x), "r"(y) : "memory"); }
__device__ __forceinline__ void sts1(uint32_t a, uint32_t v) { asm volatile("st.shared.u32 [%0], %1;" ::"r"(a), "r"(v) : "memory"); }
__device__ __forceinline__ void stsm4(uint32_t a, uint32_t r0, uint32_t r1, uint32_t r2, uint32_t r3) {
    asm volatile("stmatrix.sync.aligned.m8n8.x4.shared.b16 [%0], {%1,%2,%3,%4};" ::"r"(a), "r"(r0), "r"(r1), "r"(r2), "r"(r3));
}
__device__ __forceinline__ uint32_t pack2(float lo, float hi) { uint32_t r; asm("cvt.rn.bf16x2.f32 %0, %1, %2;" : "=r"(r) : "f"(hi), "f"(lo)); return r; }
__device__ __forceinline__ uint32_t pack2_relu(float lo, float hi) { uint32_t r; asm("cvt.rn.relu.bf16x2.f32 %0, %1, %2;" : "=r"(r) : "f"(hi), "f"(lo)); return r; }
__device__ __forceinline__ uint32_t hfma2(uint32_t a, uint32_t b, uint32_t c) { uint32_t r; asm("fma.rn.bf16x2 %0, %1, %2, %3;" : "=r"(r) : "r"(a), "r"(b), "r"(c)); return r; }
__device__ __forceinline__ uint32_t hmul2(uint32_t a, uint32_t b) { uint32_t r; asm("mul.rn.bf16x2 %0, %1, %2;" : "=r"(r) : "r"(a), "r"(b)); return r; }
__device__ __forceinline__ float bf_lo(uint32_t v) { return __uint_as_float(v << 16); }
__device__ __forceinline__ float bf_hi(uint32_t v) { return __uint_as_float(v & 0xFFFF0000u); }
__device__ __forceinline__ float bf_round(float v) { return bf_lo(pack2(v, 0.f)); }
__device__ __forceinline__ float ex2(float x) { float r; asm("ex2.approx.ftz.f32 %0, %1;" : "=f"(r) : "f"(x)); return r; }
__device__ __forceinline__ void mma16816(float* d, uint32_t a0, uint32_t a1, uint32_t a2, uint32_t a3, uint32_t b0, uint32_t b1) {
    asm("mma.sync.aligned.m16n8k16.row.col.f32.bf16.bf16.f32 {%0,%1,%2,%3}, {%4,%5,%6,%7}, {%8,%9}, {%0,%1,%2,%3};"
        : "+f"(d[0]), "+f"(d[1]), "+f"(d[2]), "+f"(d[3]) : "r"(a0), "r"(a1), "r"(a2), "r"(a3), "r"(b0), "r"(b1));
}
__device__ __forceinline__ void mma16816_first(float* d, uint32_t a0, uint32_t a1, uint32_t a2, uint32_t a3, uint32_t b0, uint32_t b1) {
    asm volatile("mma.sync.aligned.m16n8k16.row.col.f32.bf16.bf16.f32 {%0,%1,%2,%3}, {%4,%5,%6,%7}, {%8,%9}, {%10,%10,%10,%10};"
        : "=f"(d[0]), "=f"(d[1]), "=f"(d[2]), "=f"(d[3]) : "r"(a0), "r"(a1), "r"(a2), "r"(a3), "r"(b0), "r"(b1), "f"(0.f));
}
__device__ __forceinline__ void mma16816_v(float* d, uint32_t a0, uint32_t a1, uint32_t a2, uint32_t a3, uint32_t b0, uint32_t b1) {
    asm volatile("mma.sync.aligned.m16n8k16.row.col.f32.bf16.bf16.f32 {%0,%1,%2,%3}, {%4,%5,%6,%7}, {%8,%9}, {%0,%1,%2,%3};"
        : "+f"(d[0]), "+f"(d[1]), "+f"(d[2]), "+f"(d[3]) : "r"(a0), "r"(a1), "r"(a2), "r"(a3), "r"(b0), "r"(b1));
}
__device__ __forceinline__ void mma1688(float* d, uint32_t a0, uint32_t a1, uint32_t b0) {
    asm("mma.sync.aligned.m16n8k8.row.col.f32.bf16.bf16.f32 {%0,%1,%2,%3}, {%4,%5}, {%6}, {%0,%1,%2,%3};"
        : "+f"(d[0]), "+f"(d[1]), "+f"(d[2]), "+f"(d[3]) : "r"(a0), "r"(a1), "r"(b0));
}
__device__ __forceinline__ void ldsm4(uint32_t a, uint32_t* r) {
    asm volatile("ldmatrix.sync.aligned.m8n8.x4.shared.b16 {%0,%1,%2,%3}, [%4];" : "=r"(r[0]), "=r"(r[1]), "=r"(r[2]), "=r"(r[3]) : "r"(a));
}
__device__ __forceinline__ void ldsm4t(uint32_t a, uint32_t* r) {
    asm volatile("ldmatrix.sync.aligned.m8n8.x4.trans.shared.b16 {%0,%1,%2,%3}, [%4];" : "=r"(r[0]), "=r"(r[1]), "=r"(r[2]), "=r"(r[3]) : "r"(a));
}
__device__ __forceinline__ uint32_t nz(uint32_t v) { uint32_t r; asm("max.u32 %0, %1, 1;" : "=r"(r) : "r"(v)); return r; }
__device__ __forceinline__ float rcp(float x) { float r; asm("rcp.approx.ftz.f32 %0, %1;" : "=f"(r) : "f"(x)); return r; }
__device__ __forceinline__ uint2 ld_relaxed2(const void* p) { uint2 v; asm volatile("ld.relaxed.gpu.global.v2.u32 {%0,%1}, [%2];" : "=r"(v.x), "=r"(v.y) : "l"(p) : "memory"); return v; }
__device__ __forceinline__ void st_relaxed2(void* p, uint32_t x, uint32_t y) { asm volatile("st.relaxed.gpu.global.v2.u32 [%0], {%1,%2};" ::"l"(p), "r"(max(x, 1u)), "r"(max(y, 1u)) : "memory"); }
__host__ __device__ constexpr uint64_t dconst(uint32_t lbo, uint32_t sbo, uint32_t swz) {
    return ((uint64_t)(lbo >> 4) << 16) | ((uint64_t)(sbo >> 4) << 32) | ((uint64_t)swz << 62);
}
__device__ __forceinline__ uint32_t mkdesc(uint32_t addr, uint64_t c) { return (uint32_t)c | ((addr & 0x3FFFF) >> 4); }
#define WG_FENCE() asm volatile("wgmma.fence.sync.aligned;" ::: "memory")
#define WG_COMMIT() asm volatile("wgmma.commit_group.sync.aligned;" ::: "memory")
#define WG_WAIT(n) asm volatile("wgmma.wait_group.sync.aligned %0;" ::"n"(n) : "memory")
template <int N> __device__ __forceinline__ void reg_fence(float* d) {
#pragma unroll
    for (int i = 0; i < N; i++) asm volatile("" : "+f"(d[i])::"memory");
}
template <int N> __device__ __forceinline__ void reg_def(float* d) {
#pragma unroll
    for (int i = 0; i < N; i++) asm volatile("" : "=f"(d[i]));
}
template <int N> __device__ __forceinline__ void reg_def(uint32_t* d) {
#pragma unroll
    for (int i = 0; i < N; i++) asm volatile("" : "=r"(d[i]));
}
__device__ __forceinline__ bool is_unset(uint4 v) { return min(min(v.x, v.y), min(v.z, v.w)) == 0u; }
__device__ __forceinline__ uint4 nz4(uint32_t a, uint32_t b, uint32_t c, uint32_t d) { return make_uint4(max(a, 1u), max(b, 1u), max(c, 1u), max(d, 1u)); }
__device__ __forceinline__ void wait_flags(const uint32_t* p, uint32_t target, uint32_t mask) {
    int n = 0;
    while (~__ballot_sync(~0u, ld_relaxed(p) == target) & mask) { if (++n > SPIN_LIMIT) __trap(); }
    asm volatile("fence.acquire.gpu;" ::: "memory");
}
__device__ __forceinline__ float silu_bf(uint32_t cbits) {
    const float c = __uint_as_float(cbits << 16);
    return bf_round(__fdividef(c, 1.f + fminf(ex2(-1.4426950408889634f * c), 1e30f)));
}
__device__ __forceinline__ void gemv_part(uint32_t wmbuf, int wp, int lane) {
    const uint32_t wa = wmbuf + wp * 512 + (8 * (lane >> 4) + (lane & 7)) * 32 + ((lane >> 3) & 1) * 16;
    float d[4] = {};
#pragma unroll
    for (int i = 0; i < 4; i++) {
        uint32_t A[4];
        const float2 v = lds2f(wmbuf + 28672 + (wp + 8 * i) * 32 + (lane & 3) * 8);
        ldsm4t(wa + (i < 3 || wp < 4 ? i : 0) * 4096, A);
        mma16816(d, A[0], A[1], A[2], A[3], __float_as_uint(v.x), __float_as_uint(v.y));
    }
    if ((lane & 3) == 0) {
        sts1(wmbuf + 29696 + (wp * 16 + (lane >> 2)) * 4, __float_as_uint(d[0]));
        sts1(wmbuf + 29696 + (wp * 16 + 8 + (lane >> 2)) * 4, __float_as_uint(d[2]));
    }
}
__device__ __forceinline__ uint32_t mod_word(float v, int col, uint32_t target) {
    v = bf_round(v);
    if ((col >= DM && col < 2 * DM) || (col >= 4 * DM && col < 5 * DM)) v += 1.f;
    return (pack2(v, 0.f) << 16) | (target & 0xFFFFu);
}
__device__ __forceinline__ const uint4* mod_src(int i, int r, int j, bool p2) {
    i = min(i, p2 ? 251 : 223);
    return (const uint4*)g_mod + (r & 7) * (6 * DM / 4) + (i < 224 ? (p2 ? 336 : 0) + i : (i < 238 ? 14 * j + i : 14 * j + i + 322));
}
__device__ __forceinline__ void mod_store(uint32_t sb, uint4 v, const uint4* src, int i) {
    const uint32_t tag = lds1(sb + M_EPOCH) + 1;
    while (__any_sync(~0u, (((v.x ^ tag) | (v.y ^ tag) | (v.z ^ tag) | (v.w ^ tag)) & 0xFFFFu) != 0u)) v = ld_relaxed4(src);
    if (i < 224) {
        const int isc = i >= 112, c4 = i - 112 * isc;
        const uint32_t a = sb + M_ST + (c4 >> 2) * 64 + (c4 & 1) * 32 + (c4 & 2) * 4 + (isc ? 0 : 4);
        sts1(a, __byte_perm(v.x, v.y, 0x7632));
        sts1(a + 16, __byte_perm(v.z, v.w, 0x7632));
    } else if (i < 252) {
        sts4(sb + M_G + (i - 224) * 16, make_uint4(v.x & 0xFFFF0000u, v.y & 0xFFFF0000u, v.z & 0xFFFF0000u, v.w & 0xFFFF0000u));
    }
}
__device__ __forceinline__ int pass_f(int fs, int ps) { return 224 * fs + ((fs & 1) ? (ps == 0 ? 96 : ps == 1 ? 32 : 0) : (ps == 0 ? 0 : ps == 1 ? 128 : 192)); }
__device__ __forceinline__ constexpr uint32_t slot_off(int l) { return l * 16384; }
__device__ __forceinline__ constexpr int g1_slot(int s) { return s % 7; }
__device__ __noinline__ void x1_fix(const uint32_t* g, uint32_t sa, int s) {
#pragma unroll 1
    for (int k = 4 * s; k < 4 * s + 4;) {
        const uint4 v = ld_relaxed4((const uint4*)(g + k * 256));
        sts4(sa + k * 1024, v);
        k += 2 * __all_sync(~0u, min(min(v.x, v.y), min(v.z, v.w)) != 0u);
    }
    __syncwarp();
}
struct LnRow { uint32_t nm, hi, lo; };
__device__ __forceinline__ LnRow ln_coeffs(float mean, float msq) {
    const float var = bf_round(fmaxf(msq - mean * mean, 0.f));
    float sd;
    asm("sqrt.approx.f32 %0, %1;" : "=f"(sd) : "f"(bf_round(var + 1e-5f)));
    const float inv = rcp(bf_round(sd)), hi = bf_round(inv);
    LnRow c;
    c.nm = pack2(-bf_round(mean) * hi, -bf_round(mean) * hi);
    c.hi = pack2(hi, hi);
    c.lo = pack2(inv - hi, inv - hi);
    return c;
}
__device__ __forceinline__ uint32_t hadd2(uint32_t a, uint32_t b) { uint32_t r; asm("add.rn.bf16x2 %0, %1, %2;" : "=r"(r) : "r"(a), "r"(b)); return r; }
__device__ __forceinline__ uint32_t ln_norm(uint32_t x, const LnRow& c) {
    return hfma2(x, c.hi, c.nm);
}
__device__ __forceinline__ uint32_t ln_mod(uint32_t y, uint32_t sc, uint32_t sh) {
    return hfma2(y, sc, sh);
}

#define LOADW bulk_e(dst, g_wd + (size_t)((f >> 5) * 4 + nq) * 1792, 7168, bar);
template <int sec> __device__ __forceinline__ void ring_loader(const Params& p, uint32_t sb_, int r_, int j_, int lane) {
    const uint32_t sb = opaque(sb_);
    const int r = opaque(r_), j = opaque(j_), nq = j >> 1, fs = 4 * (j & 1) + nq;
    const int fa = pass_f(fs, 0), fb = pass_f(fs, 1), fc = pass_f(fs, 2);
    const uint32_t* h2src = (const uint32_t*)__shfl_sync(~0u, (unsigned long long)(p.actb + (size_t)r * RB_WORDS + RB_H2), 0);
    const CUtensorMap* gmap = (const CUtensorMap*)__shfl_sync(~0u, (unsigned long long)(&p.ga + sec), 0);
#define BAR(i) (sb + M_BAR + 8 * (i))
#define kh (j & 1)
            int sl = 0;
#pragma unroll 1
            for (int s = 0; s < 28; s++) {
                if (s == 7) { wait_flags(g_flag + (8 * r + j) * 128 + 96 + lane, lds1(sb + M_EPOCH) + 1, 0xFFFFu); fence_async_global(); }
                const int ps = s < 14 ? 0 : s < 21 ? 1 : 2;
                const uint32_t half = ps < 2 ? 8192 : 4096;
                const int sp = sl;
                if (s >= PACE && s < PACE_END) mbar_wait(BAR(B_FULL + s - PACE), 0);
                mbar_wait(BAR(B_EMPTY + sp), (s >= 7 && s < 14) || s >= 21);
                expect_e(BAR(B_FULL + sp), half);
                tma3_e(sb + slot_off(sp) + sec * half, gmap + 2 * ps, 0, ps ? 64 * sl : 32 * s, ps == 0 ? fa >> 6 : ps == 1 ? fb >> 6 : fc >> 5, BAR(B_FULL + sp));
                sl = sl == 6 ? 0 : sl + 1;
            }
            if (!sec) PROFH(3);
#pragma unroll 1
            for (int e = 0; e < 4; e++) {
                const uint32_t dst = sb + slot_off(e) + sec * 8192, bar = BAR(B_FULL + e);
                const int f = (e < 2 ? fa + 64 * e : e == 2 ? fb : fc) + 32 * sec;
                mbar_wait(BAR(B_EMPTY + e), 0);
                expect_e(bar, e == 3 && sec ? 0 : 7168);
                if (!(e == 3 && sec)) { LOADW }
            }
            sl = 4;
            int e = 4;
#pragma unroll 1
            for (int grp = 0; grp < 9; grp++) {
                const int ps = grp >= 6 ? 2 : grp >= 3 ? 1 : 0;
                int sidx = grp - 3 * ps;
                if (sec && sidx == 0) { mbar_wait(BAR(B_HRDY + ps), 0); fence_async_global(); }
                sidx += sidx >= nq;
                int f = pass_f(4 * kh + sidx, ps);
#pragma unroll 1
                for (int k = 4 >> ps; k > 0; k--, e++, f += 32) {
                    const uint32_t dst = sb + slot_off(sl), bar = BAR(B_FULL + sl);
                    mbar_wait(BAR(B_EMPTY + sl), e >= 12 && e < 24);
                    if (e < WIN_END && e >= WIN) mbar_wait(BAR(B_FULL + (sl >= WIN ? sl - WIN : sl + 12 - WIN)), e - WIN >= 12);
                    expect_e(bar, sec ? 8192 : 7168);
                    if (!sec) { LOADW }
                    else bulk_e(dst + 8192, h2src + f * 64, 8192, bar);
                    sl = sl == 11 ? 0 : sl + 1;
                }
            }
            if (!sec) PROFH(4);
}

#define PROF_PARAMS
#define PROF_ARGS
__device__ __noinline__ void helper_late(const Params& p, int r_, int j_, int warp_ PROF_PARAMS) {
    extern __shared__ __align__(1024) unsigned char smem[];
    const uint32_t sb = (uint32_t)__cvta_generic_to_shared(smem);
    const int r = opaque(r_), j = opaque(j_), warp = opaque(warp_), nq = j >> 1, b = 8 * r + j;
    uint32_t* const act = (uint32_t*)__shfl_sync(~0u, (unsigned long long)(p.actb + (size_t)r * RB_WORDS), 0);
    {
        const int lane = fresh_tid() & 31;
        const uint32_t target = lds1(sb + M_EPOCH) + 1;
        if (warp == 8) { expect_e(BAR(B_XCH), 14336); expect_e(BAR(B_XCH + 1), 14336); }
            if (warp == 9) {
#pragma unroll 1
                for (int kv = 0; kv < 2; kv++) {
                    mbar_wait(BAR(B_PUB + kv), 0);
                    wait_flags(g_flag + b * 128 + lane, target, (r >= 2 ? 6u : r == 1 ? 2u : 0u) << (8 * kv));
                    fence_async_global();
                    const uint32_t dst = sb + OFF_Y + (kv ? Y_VR : Y_K);
                    expect_e(BAR(B_KRFULL + kv), r >= 2 ? 28672 : r == 1 ? 14336 : 0);
                    if (r >= 2) bulk_e(dst, act - 2 * RB_WORDS + RB_KV + j * 7168 + kv * 3584, 14336, BAR(B_KRFULL + kv));
                    if (r >= 1) bulk_e(dst + 14336, act - RB_WORDS + RB_KV + j * 7168 + kv * 3584, 14336, BAR(B_KRFULL + kv));
                    if (kv == 0) { PROFH(8); }
                }
            } else if (warp == 8) {
                uint4 v[8];
                mbar_wait(BAR(B_WOFULL), 0);
#pragma unroll
                for (int k = 0; k < 8; k++) v[k] = ld_relaxed4(mod_src(lane + 32 * k, r, j, true));
#pragma unroll
                for (int k = 0; k < 8; k++) mod_store(sb, v[k], mod_src(lane + 32 * k, r, j, true), lane + 32 * k);
                warp_arrive(BAR(B_MOD1));
            } else if (warp == 11) {
                if (kh == 1 && r < 14) {
                    const uint32_t wmbuf = sb + OFF_X + HALF;
                    const int mcol = 2 * DM + 32 * (4 * r + nq);
                    mbar_wait(BAR(B_XFREE), 0);
                    tma3_e(wmbuf, &p.wm2, mcol, 0, 0, BAR(B_WMFULL));
                    tma3_e(wmbuf + 14336, &p.wm2, mcol, 224, 0, BAR(B_WMFULL));
#pragma unroll 1
                    for (int wd = lane; wd < 224; wd += 32) {
                        const uint32_t cb = __ldg((const uint32_t*)p.c + wd);
                        sts1(wmbuf + 28672 + (wd >> 3) * 32 + (wd & 3) * 8 + (wd & 4), pack2(silu_bf(cb & 0xFFFFu), silu_bf(cb >> 16)));
                    }
                    __syncwarp();
                    mbar_wait(BAR(B_WMFULL), 0);
                    const uint32_t wa = wmbuf + (8 * (lane >> 4) + (lane & 7)) * 64 + ((lane >> 3) & 1) * 16;
                    float d[2][4] = {};
#pragma unroll 4
                    for (int ks = 0; ks < 28; ks++) {
                        uint32_t A[8];
                        ldsm4t(wa + ks * 1024, A); ldsm4t(wa + ks * 1024 + 32, A + 4);
                        const float2 v = lds2f(wmbuf + 28672 + ks * 32 + (lane & 3) * 8);
                        mma16816(d[0], A[0], A[1], A[2], A[3], __float_as_uint(v.x), __float_as_uint(v.y));
                        mma16816(d[1], A[4], A[5], A[6], A[7], __float_as_uint(v.x), __float_as_uint(v.y));
                    }
                    const int q = lane & 3, col = mcol + 8 * q + (lane >> 2);
                    const uint32_t word = mod_word(q == 0 ? d[0][0] : q == 1 ? d[0][2] : q == 2 ? d[1][0] : d[1][2], col, target);
#pragma unroll
                    for (int i = 0; i < 8; i++) st_relaxed(g_mod + i * 6 * DM + col, word);
                }
                warp_arrive(BAR(B_WMFREE));
                mbar_wait(BAR(B_VRFULL), 0);
                l2_prefetch_e((const char*)p.wg + (size_t)b * 12544, 12544);
                l2_prefetch_e((const char*)p.wu + (size_t)b * 12544, 12544);
#pragma unroll 1
                for (int k = 0; k < (r < 12 ? 2 : 1); k++) {
                    const int u = 28 * kh + r + 16 * k;
                    expect_e(BAR(B_XFULL + k), 7168);
                    tma3_e(sb + OFF_Y + 102400, &p.dn, 0, 32 * u, 7 * j, BAR(B_XFULL + k));
                    tma3_e(sb + OFF_Y + 102400 + 3584, &p.dn, 0, 32 * u, 7 * (j ^ 1), BAR(B_XFULL + k));
                    mbar_wait(BAR(B_XFULL + k), 1);
                    asm volatile("{\n.reg .pred p;\nelect.sync _|p, 0xffffffff;\n@p cp.async.bulk.global.shared::cta.bulk_group [%0], [%1], 7168;\n"
                                 "cp.async.bulk.commit_group;\ncp.async.bulk.wait_group 0;\n}" ::"l"(g_wd + (size_t)(u * 4 + nq) * 1792), "r"(sb + OFF_Y + 102400) : "memory");
                    __syncwarp();
                }
                warp_arrive(BAR(B_FULLK));
                fence_gpu();
                if (lane < 16) st_relaxed(g_flag + (8 * lane + j) * 128 + 96 + r, target);
            }
        if (warp == 8 || warp == 11) {
            const int sec = warp == 11;
            if (sec) ring_loader<1>(p, sb, r, j, lane); else ring_loader<0>(p, sb, r, j, lane);
            mbar_wait(BAR(B_DONE), 0);
        } else if (warp == 9) {
#pragma unroll
            for (int ev = 0; ev < 4; ev++) { expect_e(BAR(B_GFULL + ev), ev < 2 ? HALF / 2 : 16384); expect_e(BAR(B_XFULL + 2 + ev), ev < 2 ? HALF / 2 : HALF - 16384); }
            mbar_wait(BAR(B_PUB + 2), 0);
            expect_e(BAR(B_FULLV), 4096); expect_e(BAR(B_FULLQ), 4096);
            const uint32_t* fp = g_flag + b * 128 + 32 + lane;
            const int par = (target - 1) & 1;
#pragma unroll 1
            for (int n = 0, ev = 0; ev < 4; n++) {
                if (ev == 1) mbar_wait(BAR(B_PUB + 3), 0);
                uint32_t ok = __ballot_sync(~0u, ld_relaxed(fp) == target) >> (8 * ev);
                while ((ok & 0xFFu) == 0xFFu) {
                    if (ev == 1) mbar_wait(BAR(B_FULLK), 1);
                    asm volatile("fence.acquire.gpu;" ::: "memory");
                    fence_async_global();
                    const int tile = (ev & 1) + (ev >> 1) * par * 2;
                    const uint32_t dst = sb + (ev == 0 ? OFF_X : OFF_Y + (ev & 1) * HALF), first = ev < 2 ? HALF / 2 : 16384;
                    const char* src = (const char*)(act + RB_O + ((ev >> 1) * 2 + tile) * 14336);
                    if (ev >= 2) bulk_e(sb + OFF_X + X_STAT + (ev & 1) * 49152, act + RB_ST + tile * 1024, 4096, BAR(B_FULLV + (ev & 1)));
                    bulk_e(dst, src, first, BAR(B_GFULL + ev));
                    bulk_e(dst + first, src + first, HALF - first, BAR(B_XFULL + 2 + ev));
                    if (ev) PROFH(4 + ev);
                    ev++; ok >>= 8;
                }
                if (n > SPIN_LIMIT) __trap();
            }
            mbar_wait(BAR(B_XFULL + 5), 1);
#pragma unroll 1
            for (int hf = 0; hf < 2; hf++) {
                const int tile = (par ^ 1) * 2 + hf;
                uint4* xz = (uint4*)(act + RB_X1 + tile * 14336 + j * 1792) + lane;
#pragma unroll
                for (int i = 0; i < 14; i++) xz[i * 32] = make_uint4(0, 0, 0, 0);
                ((uint4*)(act + RB_ST + (tile * 8 + j) * 128))[lane] = make_uint4(0, 0, 0, 0);
            }
#pragma unroll 1
            for (int ps = 0; ps < 3; ps++) {
                mbar_wait(BAR(B_PUB + 6 + ps), 0);
                wait_flags(g_flag + b * 128 + 64 + lane, target, (0x55u << kh) << (8 * ps));
                warp_arrive(BAR(B_HRDY + ps));
                PROFH(9 + ps);
            }
        } else {
#pragma unroll 1
            for (int k = 0; k < 9; k++) {
                uint32_t* fp = k < 2 ? g_flag + (b + 8 * lane) * 128 + k * 8 + lane : g_flag + (8 * r + lane) * 128 + 16 + k * 8 + j;
                mbar_wait(BAR(B_PUB + k), 0);
                if (k != 4 && k != 5) fence_gpu();
                if (k < 2 ? (lane == 1 || lane == 2) : lane < 8) st_relaxed(fp, target);
                if (k >= 3 && k <= 5) PROFH(k - 3);
            }
        }
    }
}

__global__ void __cluster_dims__(2, 1, 1) __launch_bounds__(384, 1) fused_block_kernel(const __grid_constant__ Params p) {
    extern __shared__ __align__(1024) unsigned char smem[];
    const uint32_t sb = (uint32_t)__cvta_generic_to_shared(smem);
    const int tid = threadIdx.x, lane = tid & 31, warp = __shfl_sync(~0u, tid >> 5, 0);
    const int m = blockIdx.x >> 1;
    int r, nq;
    if (m < 4) { r = 15; nq = m; }
    else if (m < 36) { r = (m - 4) & 7; nq = (m - 4) >> 3; }
    else { nq = (m - 36) / 7; r = m - 28 - 7 * nq; }
    const int j = opaque(2 * nq + (blockIdx.x & 1)), b = 8 * r + j, fs = 4 * kh + nq;
#define act (p.actb + (size_t)r * RB_WORDS)
    constexpr uint32_t sc = 0;
    if (lane == 0 && warp < 9 && warp != 6 && warp != 7) {
        const int i0 = warp == 8 ? 0 : 8 + 8 * warp, cnt = warp == 0 || warp == 8 ? 1 : warp < 3 ? 2 : 8;
#pragma unroll
        for (int k = 0; k < 8; k++) if (i0 + k != B_WMFULL) mbar_init(BAR(i0 + k), cnt);
        if (warp == 8) mbar_init(BAR(B_WMFULL), 1);
        asm volatile("fence.mbarrier_init.release.cluster;" ::: "memory");
        fence_async_smem();
    }

    if (warp >= 8) {
        const int lane = fresh_tid() & 31;
        const bool early = kh == 0, gemv = r < 14;
        const int mcol = early ? 16 * (4 * r + nq) : 2 * DM + 32 * (4 * r + nq);
        const uint32_t wmbuf = sb + OFF_Y + HALF;
        if (warp == 8) {
            __syncwarp();
            expect_e(BAR(B_WMFULL), gemv ? 28672 >> early : 0);
            if (early && gemv) { tma3_e(wmbuf, &p.wm, mcol, 0, 0, BAR(B_WMFULL)); tma3_e(wmbuf + 7168, &p.wm, mcol, 224, 0, BAR(B_WMFULL)); }
#pragma unroll
            for (int kb = 0; kb < XFIRST; kb++) {
                expect_e(BAR(B_XFULL + kb), 16384);
                tma3_e(sb + OFF_X + kb * 16384, &p.xm, 64 * kb, 128 * r, 0, BAR(B_XFULL + kb));
            }
        }
        asm volatile("setmaxnreg.dec.sync.aligned.u32 56;");
        if (warp == 9) {
#pragma unroll
            for (int i = 56; i < 64; i++) init_e(BAR(i), 1);
            fence_async_smem();
        }
        bar_arrive(0, 384);
        asm volatile("barrier.cluster.arrive.relaxed.aligned;" ::: "memory");
        if (warp == 8) {
#pragma unroll
            for (int kb = XFIRST; kb < 7; kb++) {
                expect_e(BAR(B_XFULL + kb), 16384);
                tma3_e(sb + OFF_X + kb * 16384, &p.xm, 64 * kb, 128 * r, 0, BAR(B_XFULL + kb));
            }
            if (KDELAY >= 0) { mbar_wait(BAR(B_XFULL + KDELAY), 0); l2_prefetch_e((const char*)p.wqkv + (size_t)b * 9408, 9408); }
#pragma unroll 1
            for (int mt = 0; mt < 4; mt++) {
                if (mt == 1) bar_sync(9, 384);
                if (mt == 3) mbar_wait(BAR(B_WMFREE), 0);
                if (mt == 1 && early) mbar_wait(BAR(B_WMFREE), 0);
                if (mt) mbar_wait(BAR(mt == 1 ? (VGATE == 1 ? B_XFREE : B_FULLK) : mt == 2 ? B_MOD1 : B_VRFULL), 0);
                const uint32_t bar = BAR(mt == 3 ? B_WOFULL : B_FULLK + mt), dst = sb + (mt < 2 ? OFF_Y : OFF_X) + (mt & 1) * HALF;
                const int c0 = (mt < 2 ? DM + DM * mt : 0) + 56 * j - 8 * kh;
                if (!sc) {
                    expect_e(bar, HALF);
                    tma3_e(dst, mt == 3 ? &p.wo : &p.qkv, c0, 0, 0, bar);
                    tma3_e(dst + HALF / 2, mt == 3 ? &p.wo : &p.qkv, c0, 224, 0, bar);
                }
            }
        } else {
            if (KDELAY < 0 && warp == 10) l2_prefetch_e((const char*)p.wqkv + (size_t)b * 9408, 9408);
            bar_sync(9, 384);
            if (sc) return;
            if (warp == 11 && early) {
                const uint32_t target = lds1(sb + M_EPOCH) + 1;
                mbar_wait(BAR(B_GEMV), 0);
                float sum = 0.f;
#pragma unroll
                for (int i = 0; i < 8; i++) sum += *(const float*)(smem + OFF_Y + HALF + 29696 + (i * 16 + (lane & 15)) * 4);
                uint32_t* mg = g_mod + mcol + (lane & 15) + (lane >> 4) * 4 * 6 * DM;
                const uint32_t word = mod_word(sum, mcol, target);
                if (gemv) { st_relaxed(mg, word); st_relaxed(mg + 6 * DM, word); st_relaxed(mg + 12 * DM, word); st_relaxed(mg + 18 * DM, word); }
            }
        }
    }
    if (LIKELY(warp < 8)) {
        const int w = warp >> 2, wi = warp & 3;
#define COORDS const int t = fresh_tid() & 127, lane = t & 31, q = lane & 3, lr = lane >> 2, ra = 64 * w + 16 * wi + lr; \
        const uint32_t lx = (lane >> 4) ^ (lane & 7), mrow = (64 * w + 16 * wi + ((lane >> 3) & 1) * 8 + (lane & 7)) * 128; \
        (void)q; (void)lr; (void)ra; (void)lx; (void)mrow;
        const int sid = 2 * (j & 3) + w;
#define RUN(k) (!sc || sid == (k))
#define WAIT(i, par) mbar_wait_c(BAR(i), (par) | sc)
        constexpr uint64_t DB128 = dconst(4096, 1024, 1);
        {
            const int wd = fresh_tid();
            const uint32_t cb = wd < 224 ? __ldg((const uint32_t*)p.c + wd) : 0u;
            if (wd == 255 && !sc) sts1(sb + M_EPOCH, atomicAdd(&g_ticket, 1u) / NCTA);
            sts1(sb + OFF_Y + HALF + 28672 + (wd >> 3) * 32 + (wd & 3) * 8 + (wd & 4), pack2(silu_bf(cb & 0xFFFFu), silu_bf(cb >> 16)));
        }
        bar_arrive(9, 384);
        bar_sync(0, 384);
        asm volatile("barrier.cluster.arrive.relaxed.aligned;" ::: "memory");
        asm volatile("setmaxnreg.inc.sync.aligned.u32 224;");
        PROFC(0);
        uint32_t xr[16];
        {
            COORDS
            uint32_t h[112];
            LnRow ca, cb;
            const int mi = min(128 * w + t, 223);
            const uint4* msrc = mod_src(mi, r, j, false);
            uint4 mv;
            {
                float ds[4] = {}, da[2][4] = {}, db[2][4] = {};
                const uint32_t ONE2 = 0x3F803F80u;
#pragma unroll
                for (int kb = 0; kb < 7; kb++) {
                    if (kb == GEMV_AT && kh == 0) { WAIT(B_WMFULL, 0); gemv_part(sb + OFF_Y + HALF, warp, lane); warp_arrive(BAR(B_GEMV)); }
                    WAIT(B_XFULL + kb, 0);
#pragma unroll
                    for (int k4 = 0; k4 < 4; k4++) ldsm4(sb + OFF_X + mrow + kb * 16384 + (((2 * k4) ^ lx) << 4), h + 16 * kb + 4 * k4);
#pragma unroll
                    for (int k4 = 0; k4 < 4; k4++) {
                        const uint32_t* f = h + 16 * kb + 4 * k4;
                        mma16816(ds, f[0], f[1], f[2], f[3], ONE2, ONE2);
                        mma1688(da[0], f[0], f[1], f[0]); mma1688(db[0], f[0], f[1], f[1]);
                        mma1688(da[1], f[2], f[3], f[2]); mma1688(db[1], f[2], f[3], f[3]);
                    }
                }
#pragma unroll
                for (int i = 0; i < 4; i++) {
                    const int ch = 7 * j + 2 * i + (lane >> 4);
                    ldsm4(sb + OFF_X + mrow + (ch >> 3) * 16384 + (((ch ^ lane) & 7) << 4), xr + 4 * i);
                }
                mv = ld_relaxed4(msrc);
                warp_arrive(BAR(B_XFREE));
                float qa = (lr & 1) ? da[0][1] + da[1][1] : da[0][0] + da[1][0];
                float qb = (lr & 1) ? db[0][3] + db[1][3] : db[0][2] + db[1][2];
                const int src = (lane & ~3) | (lr >> 1);
                qa = __shfl_sync(~0u, qa, src);
                qb = __shfl_sync(~0u, qb, src);
                ca = ln_coeffs(ds[0] * (1.f / DM), qa * (1.f / DM));
                cb = ln_coeffs(ds[2] * (1.f / DM), qb * (1.f / DM));
#pragma unroll
                for (int i = 0; i < 4 * NPRE; i += 2) { h[i] = ln_norm(h[i], ca); h[i + 1] = ln_norm(h[i + 1], cb); }
            }
            PROFC(1);
            {
                float ak[28], av[28], aq[28];
                uint32_t kp[14], vp[14];
                const uint64_t bq0 = (DB128 & ~0xFFFFFFFFull) | (mkdesc(sb + OFF_X, DB128) + kh), bk0 = bq0 + (OFF_Y >> 4), bv0 = bk0 + (HALF >> 4);
                uint32_t* kvg = act + RB_KV + j * 7168 + (8 * w + 2 * wi) * 224 + lane;
                mod_store(sb, mv, msrc, mi);
                bar_sync(3, 256);
                if (warp == 0) warp_arrive(BAR(B_MOD1));
                WAIT(B_FULLK, 0);
                PROFC(2);
                reg_def<28>(ak);
#pragma unroll
                for (int g4 = 0; g4 < 4; g4++) {
#pragma unroll
                    for (int ks = 7 * g4; ks < 7 * g4 + 7; ks++) {
                        const uint4 st = *(const uint4*)(smem + M_ST + ks * 64 + q * 16);
                        if (ks >= NPRE) {
                            h[4 * ks] = ln_norm(h[4 * ks], ca); h[4 * ks + 1] = ln_norm(h[4 * ks + 1], cb);
                            h[4 * ks + 2] = ln_norm(h[4 * ks + 2], ca); h[4 * ks + 3] = ln_norm(h[4 * ks + 3], cb);
                        }
                        h[4 * ks] = ln_mod(h[4 * ks], st.x, st.y); h[4 * ks + 1] = ln_mod(h[4 * ks + 1], st.x, st.y);
                        h[4 * ks + 2] = ln_mod(h[4 * ks + 2], st.z, st.w); h[4 * ks + 3] = ln_mod(h[4 * ks + 3], st.z, st.w);
                    }
                    WG_FENCE();
#pragma unroll
                    for (int ks = 7 * g4; ks < 7 * g4 + 7; ks++) wgmma_rl_56(ak, h[4 * ks], h[4 * ks + 1], h[4 * ks + 2], h[4 * ks + 3], bk0 + ks * 128, ks != 0);
                }
                WG_COMMIT();
                PROFC(3);
                reg_def<28>(av);
                WG_WAIT(0);
                reg_fence<28>(ak);
#pragma unroll
                for (int g = 0; g < 7; g++) {
                    kp[2 * g] = pack2(ak[4 * g], ak[4 * g + 1]); kp[2 * g + 1] = pack2(ak[4 * g + 2], ak[4 * g + 3]);
                    kvg[g * 32] = kp[2 * g]; kvg[224 + g * 32] = kp[2 * g + 1];
                }
                warp_arrive(BAR(B_PUB));
                PROFC(4);
                if (KEARLY) WAIT(B_FULLV, 0);
                WG_FENCE();
#pragma unroll
                for (int ks = KEARLY ? 0 : 8; ks < 28; ks++) wgmma_rl_56(av, h[4 * ks], h[4 * ks + 1], h[4 * ks + 2], h[4 * ks + 3], bv0 + ks * 128, ks != 0);
                WG_COMMIT();
                reg_def<28>(aq);
                WAIT(B_FULLQ, 0);
                WG_FENCE();
#pragma unroll
                for (int ks = 0; ks < VPRE; ks++) wgmma_rl_56(aq, h[4 * ks], h[4 * ks + 1], h[4 * ks + 2], h[4 * ks + 3], bq0 + ks * 128, ks != 0);
                WG_COMMIT();
                WG_WAIT(1);
                reg_fence<28>(av);
#pragma unroll
                for (int g = 0; g < 7; g++) {
                    vp[2 * g] = pack2(av[4 * g], av[4 * g + 1]); vp[2 * g + 1] = pack2(av[4 * g + 2], av[4 * g + 3]);
                    kvg[3584 + g * 32] = vp[2 * g]; kvg[3584 + 224 + g * 32] = vp[2 * g + 1];
                }
                warp_arrive(BAR(B_PUB + 1));
                PROFC(5);
                if (!VPRE) WAIT(B_FULLQ, 0);
                WG_FENCE();
#pragma unroll
                for (int ks = VPRE; ks < 28; ks++) wgmma_rl_56(aq, h[4 * ks], h[4 * ks + 1], h[4 * ks + 2], h[4 * ks + 3], bq0 + ks * 128, ks != 0);
                WG_COMMIT();
                WAIT(B_PUB + 1, 0);
                const uint32_t rg = 8 * w + 2 * wi + ((lane >> 3) & 1);
                const uint32_t ko = sb + OFF_Y + Y_KOWN + rg * 896 + (lane & 7) * 16, qo = sb + OFF_Y + Y_Q + rg * 1024 + (lane >> 4) * 128 + (lane & 7) * 16;
#pragma unroll
                for (int g = 0; g < 6; g += 2) {
                    stsm4(ko + (g + (lane >> 4)) * 128, kp[2 * g], kp[2 * g + 1], kp[2 * g + 2], kp[2 * g + 3]);
                    stsm4(ko + (Y_VOWN - Y_KOWN) + (g + (lane >> 4)) * 128, vp[2 * g], vp[2 * g + 1], vp[2 * g + 2], vp[2 * g + 3]);
                }
                stsm4(ko + (lane >> 4) * (Y_VOWN - Y_KOWN) + 6 * 128, kp[12], kp[13], vp[12], vp[13]);
                WG_WAIT(0);
                reg_fence<28>(aq);
                __syncwarp();
                if (lane < 3 && w == 1) mbar_arrive(BAR(B_EMPTY + lane));
                uint32_t qp[14];
#pragma unroll
                for (int i = 0; i < 14; i++) qp[i] = pack2(aq[2 * i], aq[2 * i + 1]);
                stsm4(qo, qp[0], qp[1], qp[2], qp[3]);
                stsm4(qo + 256, qp[4], qp[5], q < 2 ? qp[6] : 0u, q < 2 ? qp[7] : 0u);
                stsm4(qo + 512, q < 2 ? 0u : qp[6], q < 2 ? 0u : qp[7], qp[8], qp[9]);
                stsm4(qo + 768, qp[10], qp[11], qp[12], qp[13]);
                fence_async_smem();
                if (!sc) bar_sync(3, 256);
            }
        }
        PROFC(6);
        WAIT(B_KRFULL, 0);
        if (ATT_OFF && w == ATT_WG) { const uint32_t t0 = clock(); while (clock() - t0 < ATT_OFF) {} }
        PROFC(7);
        if (RUN(2)) {
#pragma unroll 1
            for (int hf = sc; hf < 2; hf++) {
                COORDS
                float s[160];
                const float CS = 0.18898223650461361f * 1.4426950408889634f;
                const float NEG = __int_as_float(0xFF800000);
                constexpr uint64_t DQ = dconst(128, 1024, 0), DK = dconst(128, 896, 0);
                {
                    const uint32_t qd = mkdesc(sb + OFF_Y + Y_Q + hf * 8192 + w * 512, DQ), kd = mkdesc(sb + OFF_Y + Y_K + hf * 8 * 896 + w * 384, DK);
                    reg_def<160>(s);
                    WG_FENCE();
                    wgmma_sk_160<DQ, DK>(s, qd, kd, 0);
                    wgmma_sk_160<DQ, DK>(s, qd + 16, kd + 16, 1);
                    wgmma_sk_160<DQ, DK>(s + 80, qd, kd + 20 * 56, 0);
                    wgmma_sk_160<DQ, DK>(s + 80, qd + 16, kd + 20 * 56 + 16, 1);
                    WG_COMMIT();
                    WG_WAIT(0);
                    reg_fence<160>(s);
                }
                if (r < 2) {
                    const int pmin = 4 - 2 * r - hf;
#pragma unroll
                    for (int p4 = 0; p4 < 4; p4++)
                        if (p4 < pmin) {
#pragma unroll
                            for (int i = 0; i < 32; i++) asm volatile("mov.b32 %0, 0xFF800000;" : "=f"(s[32 * p4 + i]));
                        }
                }
                const bool c0 = 2 * q > lr, c1 = 2 * q + 1 > lr;
#pragma unroll
                for (int pp = 0; pp < 4; pp++) {
                    const bool me = pp == wi;
                    float* e = s + 8 * pp;
                    if (me && !c0) { e[0] = NEG; e[6] = NEG; }
                    if (me && !c1) { e[1] = NEG; e[7] = NEG; }
                    if (me) { e[2] = NEG; e[3] = NEG; }
                    e = s + 8 * (pp + 16);
                    if (me && c0) { e[0] = NEG; e[6] = NEG; }
                    if (me && c1) { e[1] = NEG; e[7] = NEG; }
                    if (me) { e[4] = NEG; e[5] = NEG; }
                }
#pragma unroll
                for (int i = 0; i < 24; i++) s[i] = (i >> 3) < wi ? s[136 + i] : s[i];
                int i0 = 0x80000000, i1 = 0x80000000, i2 = 0x80000000, i3 = 0x80000000;
#pragma unroll
                for (int pp = 0; pp < 17; pp++) {
                    const float* e = s + 8 * pp;
                    i0 = __vimax3_s32(i0, __float_as_int(e[0]), __float_as_int(e[1])); i1 = __vimax3_s32(i1, __float_as_int(e[2]), __float_as_int(e[3]));
                    i2 = __vimax3_s32(i2, __float_as_int(e[4]), __float_as_int(e[5])); i3 = __vimax3_s32(i3, __float_as_int(e[6]), __float_as_int(e[7]));
                }
                i0 = max(i0, i2); i1 = max(i1, i3);
                i0 = max(i0, __shfl_xor_sync(~0u, i0, 1)); i1 = max(i1, __shfl_xor_sync(~0u, i1, 1));
                i0 = max(i0, __shfl_xor_sync(~0u, i0, 2)); i1 = max(i1, __shfl_xor_sync(~0u, i1, 2));
                if (__any_sync(~0u, (i0 | i1) < 0)) {
                    uint32_t u0 = ~0u, u1 = ~0u, u2 = ~0u, u3 = ~0u;
#pragma unroll
                    for (int pp = 0; pp < 17; pp++) {
                        const float* e = s + 8 * pp;
                        u0 = __vimin3_u32(u0, __float_as_uint(e[0]), __float_as_uint(e[1])); u1 = __vimin3_u32(u1, __float_as_uint(e[2]), __float_as_uint(e[3]));
                        u2 = __vimin3_u32(u2, __float_as_uint(e[4]), __float_as_uint(e[5])); u3 = __vimin3_u32(u3, __float_as_uint(e[6]), __float_as_uint(e[7]));
                    }
                    u0 = min(u0, u2); u1 = min(u1, u3);
                    u0 = min(u0, __shfl_xor_sync(~0u, u0, 1)); u1 = min(u1, __shfl_xor_sync(~0u, u1, 1));
                    u0 = min(u0, __shfl_xor_sync(~0u, u0, 2)); u1 = min(u1, __shfl_xor_sync(~0u, u1, 2));
                    if (i0 < 0) i0 = u0;
                    if (i1 < 0) i1 = u1;
                }
                const float ma = __int_as_float(i0), mb = __int_as_float(i1);
                const float na = -ma * CS, nb = -mb * CS;
                PROFC(8 + 3 * hf);
                {
                    WAIT(B_VRFULL, 0);
                    float o[16] = {}, rs[4] = {};
                    const uint32_t va = sb + OFF_Y + Y_VR + (8 * hf + ((lane >> 3) & 1)) * 896 + (3 * w + (lane >> 4)) * 128 + (lane & 7) * 16;
                    constexpr uint32_t OWN = Y_VOWN - 32 * 896;
#pragma unroll
                    for (int pp = 0; pp < 17; pp++) {
                        uint32_t B[8];
                        const uint32_t v = va + pp * 1792 + (pp < 3 ? (pp < wi ? 17 * 1792 + OWN : 0) : pp == 16 ? OWN : pp >= 12 ? hf * OWN : 0);
                        ldsm4t(v, B); ldsm4t(v + 256, B + 4);
                        float e[8];
#pragma unroll
                        for (int i = 0; i < 8; i++) e[i] = ex2(fmaf(s[8 * pp + i], CS, (i & 2) ? nb : na));
                        const uint32_t p0 = pack2(e[0], e[1]), p1 = pack2(e[2], e[3]), p2 = pack2(e[4], e[5]), p3 = pack2(e[6], e[7]);
                        mma16816(rs, p0, p1, p2, p3, 0x3F803F80u, 0x3F803F80u);
#pragma unroll
                        for (int g = 0; g < 4; g++) mma16816(o + 4 * g, p0, p1, p2, p3, B[2 * g], B[2 * g + 1]);
                    }
                    PROFC(9 + 3 * hf);
                    const float ia = rcp(rs[0]), ib = rcp(rs[2]);
                    uint32_t* og = act + RB_O + hf * 14336 + (7 * j + 3 * w) * 256 + wi * 64 + lane;
#pragma unroll
                    for (int g = 0; g < 4; g++) {
                        if ((g == 3 - 3 * w) ? ((q >> 1) == w) : true) {
                            og[g * 256] = pack2(o[4 * g] * ia, o[4 * g + 1] * ia);
                            og[g * 256 + 32] = pack2(o[4 * g + 2] * ib, o[4 * g + 3] * ib);
                        }
                    }
                    warp_arrive(BAR(B_PUB + 2 + hf));
                    PROFC(10 + 3 * hf);
                }
            }
        }
        uint32_t x1p[14];
        COORDS
        constexpr uint64_t DT = dconst(1024, 128, 0);
        const int tile = opaque((lds1(sb + M_EPOCH) & 1) * 2 + w);
        if (RUN(4)) {
            float ac[28];
            const uint32_t ad = mkdesc(sb + (w ? OFF_Y + HALF : OFF_X), DT), bd = mkdesc(sb + OFF_X + HALF, DB128) + kh;
            WAIT(B_WOFULL, 0);
            WAIT(B_MOD1, 1);
            WAIT(B_GFULL + w, 0);
            PROFC(28);
            reg_def<28>(ac);
#pragma unroll 1
            for (int u = 0; u < 4; u++) {
                if (u == 2) WAIT(B_XFULL + 2 + w, 1);
                WG_FENCE();
#pragma unroll
                for (int i = 0; i < 7; i++) wgmma_ss_56<DT, DB128>(ac, ad + (7 * u + i) * 128, bd + (7 * u + i) * 128, (u | i) != 0);
            }
            WG_COMMIT();
            WG_WAIT(0);
            reg_fence<28>(ac);
            PROFC(14);
            __syncwarp();
            if (lane < 3) mbar_arrive(BAR(B_EMPTY + 4 - w + lane));
            if (lane < 3 && w == 0) mbar_arrive(BAR(B_EMPTY + lane));
            float ds[4] = {}, da[4] = {}, db[4] = {};
            uint32_t* xo = act + RB_X1 + tile * 14336 + 7 * j * 256 + wi * 64 + lane;
#pragma unroll
            for (int g = 0; g < 7; g++) {
                const float2 ga = *(const float2*)(smem + M_G + (8 * g + 2 * q) * 4);
                x1p[2 * g] = pack2(fmaf(ga.x, ac[4 * g], bf_lo(xr[2 * g])), fmaf(ga.y, ac[4 * g + 1], bf_hi(xr[2 * g])));
                x1p[2 * g + 1] = pack2(fmaf(ga.x, ac[4 * g + 2], bf_lo(xr[2 * g + 1])), fmaf(ga.y, ac[4 * g + 3], bf_hi(xr[2 * g + 1])));
                st_relaxed(xo + g * 256, nz(x1p[2 * g])); st_relaxed(xo + g * 256 + 32, nz(x1p[2 * g + 1]));
                mma1688(ds, x1p[2 * g], x1p[2 * g + 1], 0x3F803F80u);
                mma1688(da, x1p[2 * g], x1p[2 * g + 1], x1p[2 * g]);
                mma1688(db, x1p[2 * g], x1p[2 * g + 1], x1p[2 * g + 1]);
            }
            const int src = (lane & ~3) | (lr >> 1);
            const float qa = __shfl_sync(~0u, (lr & 1) ? da[1] : da[0], src), qb = __shfl_sync(~0u, (lr & 1) ? db[3] : db[2], src);
            const float kk = (q & 1) ? ((q & 2) ? qb : qa) : ((q & 2) ? ds[2] : ds[0]);
            st_relaxed(act + RB_ST + ((tile * 8 + j) * 64 + 16 * wi + lr + 4 * (q & 2)) * 2 + (q & 1), nz(__float_as_uint(kk)));
            __syncwarp();
            if (lane < 2) mbar_arrive(BAR(B_PUB + 4 + w));
        } else reg_def<14>(x1p);
        PROFC(15);
        uint32_t h2a[32], h2b[24];
        {
            const int fa = pass_f(fs, 0), fb = pass_f(fs, 1), fc = pass_f(fs, 2);
            uint32_t* h2g = act + RB_H2 + (8 * w + 2 * wi) * 32 + lane;
            const uint32_t a0 = mkdesc(sb + OFF_Y + w * HALF, DT);
            if (RUN(3)) {
                LnRow ca, cb;
                {
                    const uint32_t* sg = act + RB_ST + ((tile * 8 + 2 * q) * 64 + 16 * wi + lr) * 2;
                    uint2 u[4];
                    WAIT(B_FULLV + w, 1);
                    PROFC(16);
#pragma unroll
                    for (int i = 0; i < 4; i++) { const float2 v = lds2f(sb + OFF_X + X_STAT + w * 49152 + ((2 * q + (i >> 1)) * 64 + 16 * wi + lr + 8 * (i & 1)) * 8); u[i] = make_uint2(__float_as_uint(v.x), __float_as_uint(v.y)); }
                    while (__any_sync(~0u, min(min(min(u[0].x, u[0].y), min(u[1].x, u[1].y)), min(min(u[2].x, u[2].y), min(u[3].x, u[3].y))) < 1u - sc)) {
#pragma unroll
                        for (int i = 0; i < 4; i++) u[i] = ld_relaxed2(sg + (i >> 1) * 128 + (i & 1) * 16);
                    }
                    warp_arrive(BAR(B_EMPTY + 3 + 3 * w));
                    float v[4] = {__uint_as_float(u[0].x) + __uint_as_float(u[2].x), __uint_as_float(u[0].y) + __uint_as_float(u[2].y),
                                  __uint_as_float(u[1].x) + __uint_as_float(u[3].x), __uint_as_float(u[1].y) + __uint_as_float(u[3].y)};
#pragma unroll
                    for (int i = 0; i < 4; i++) { v[i] += __shfl_xor_sync(~0u, v[i], 1); v[i] += __shfl_xor_sync(~0u, v[i], 2); }
                    ca = ln_coeffs(v[0] * (1.f / DM), v[1] * (1.f / DM));
                    cb = ln_coeffs(v[2] * (1.f / DM), v[3] * (1.f / DM));
                }
                const uint32_t ha = sb + OFF_Y + w * HALF + (lane >> 4) * 1024 + (2 * wi + ((lane >> 3) & 1)) * 128 + (lane & 7) * 16;
                const uint32_t sta = sb + M_ST + q * 16;
                const uint32_t* xg = act + RB_X1 + tile * 14336 + (lane >> 4) * 256 + wi * 64 + (lane & 15) * 4;
                uint32_t x[8];
                const uint32_t xs = sb + OFF_Y + w * HALF + (lane >> 4) * 1024 + wi * 256 + (lane & 15) * 16;
                uint4 st[2];
                auto load = [&](int s) {
                    if (s == 4) mbar_wait_c(BAR(B_XFULL + 4 + w), 1);
                    ldsm4(ha + s * 4096, x); ldsm4(ha + s * 4096 + 2048, x + 4);
                    st[0] = lds4(sta + s * 128); st[1] = lds4(sta + s * 128 + 64);
                };
                auto prep = [&](int s, uint32_t* f) {
                    if (__any_sync(~0u, min(min(min(x[0], x[1]), min(x[2], x[3])), min(min(x[4], x[5]), min(x[6], x[7]))) < 1u - sc)) {
                        WG_WAIT(0);
                        x1_fix(xg, xs, s);
                        ldsm4(ha + s * 4096, x); ldsm4(ha + s * 4096 + 2048, x + 4);
                    }
#pragma unroll
                    for (int i = 0; i < 2; i++) {
                        f[4 * i] = ln_mod(ln_norm(x[4 * i], ca), st[i].x, st[i].y); f[4 * i + 1] = ln_mod(ln_norm(x[4 * i + 1], cb), st[i].x, st[i].y);
                        f[4 * i + 2] = ln_mod(ln_norm(x[4 * i + 2], ca), st[i].z, st[i].w); f[4 * i + 3] = ln_mod(ln_norm(x[4 * i + 3], cb), st[i].z, st[i].w);
                    }
                    if (s < 13) load(s + 1);
                    stsm4(ha + s * 4096, f[0], f[1], f[2], f[3]); stsm4(ha + s * 4096 + 2048, f[4], f[5], f[6], f[7]);
                };
                float ac[128];
                uint32_t fr[3][8];
                uint64_t bd = (DB128 & ~0xFFFFFFFFull) | mkdesc(sb, DB128);
                reg_def<128>(ac);
                WAIT(B_GFULL + 2 + w, 0);
                load(0);
                prep(0, fr[0]);
                PROFC(17);
#pragma unroll
                for (int s = 0; s < 14; s++) {
                    const uint32_t* f = fr[s % 3];
                    WAIT(B_FULL + g1_slot(s), s >= 7);
                    WG_FENCE();
                    wgmma_rl_256(ac, f[0], f[1], f[2], f[3], bd, s != 0);
                    wgmma_rl_256(ac, f[4], f[5], f[6], f[7], bd + 128, 1);
                    bd += s == 6 ? p.zero - 6 * 1024ull : 1024;
                    WG_COMMIT();
                    if (s < 13) prep(s + 1, fr[(s + 1) % 3]);
                    if (s > 0) { WG_WAIT(1); warp_arrive(BAR(B_EMPTY + g1_slot(s - 1))); }
                }
                fence_async_smem();
                PROFC(18);
                WG_WAIT(0);
                reg_fence<128>(ac);
                warp_arrive(BAR(B_EMPTY + 6));
#pragma unroll
                for (int g = 0; g < 16; g++) {
                    h2a[2 * g] = hmul2(pack2_relu(ac[4 * g], ac[4 * g + 1]), pack2(ac[64 + 4 * g], ac[64 + 4 * g + 1]));
                    h2a[2 * g + 1] = hmul2(pack2_relu(ac[4 * g + 2], ac[4 * g + 3]), pack2(ac[64 + 4 * g + 2], ac[64 + 4 * g + 3]));
                }
                bar_sync(1 + w, 128);
            } else reg_def<32>(h2a);
            PROFC(19);
            if (RUN(5)) {
                float ac[64];
                reg_def<64>(ac);
                const uint32_t bx = mkdesc(sb, dconst(8192, 1024, 1));
#pragma unroll kB
                for (int s = 0; s < 7; s++) {
                    WAIT(B_FULL + s, 0);
                    const uint32_t ad = a0 + s * 512, bd = bx + (slot_off(s) >> 4);
                    WG_FENCE();
#pragma unroll
                    for (int k = 0; k < 4; k++) wgmma_ss_128<DT, DB128>(ac, ad + k * 128, bd + k * 128, (s | k) != 0);
                    WG_COMMIT();
                    if (s == 1) {
#pragma unroll
                        for (int g = 0; g < 16; g++) { h2g[(fa / 8 + g) * 512] = h2a[2 * g]; h2g[(fa / 8 + g) * 512 + 32] = h2a[2 * g + 1]; }
                        warp_arrive(BAR(B_PUB + 6));
                    }
                    if (s > 0) { WG_WAIT(1); warp_arrive(BAR(B_EMPTY + s - 1)); }
                }
                WG_WAIT(0);
                reg_fence<64>(ac);
                warp_arrive(BAR(B_EMPTY + 6));
#pragma unroll
                for (int g = 0; g < 8; g++) {
                    h2b[2 * g] = hmul2(pack2_relu(ac[4 * g], ac[4 * g + 1]), pack2(ac[32 + 4 * g], ac[32 + 4 * g + 1]));
                    h2b[2 * g + 1] = hmul2(pack2_relu(ac[4 * g + 2], ac[4 * g + 3]), pack2(ac[32 + 4 * g + 2], ac[32 + 4 * g + 3]));
                }
            } else reg_def<16>(h2b);
            PROFC(27);
            if (RUN(6)) {
                float ac[32];
                reg_def<32>(ac);
                const uint32_t bx = mkdesc(sb, dconst(4096, 512, 2));
#pragma unroll kC
                for (int s = 0; s < 7; s++) {
                    WAIT(B_FULL + s, 1);
                    const uint32_t ad = a0 + s * 512, bd = bx + (slot_off(s) >> 4);
                    WG_FENCE();
#pragma unroll
                    for (int k = 0; k < 4; k++) wgmma_ss_64<DT, dconst(4096, 512, 2)>(ac, ad + k * 128, bd + k * 64, (s | k) != 0);
                    WG_COMMIT();
                    if (s == 1) {
#pragma unroll
                        for (int g = 0; g < 8; g++) { h2g[(fb / 8 + g) * 512] = h2b[2 * g]; h2g[(fb / 8 + g) * 512 + 32] = h2b[2 * g + 1]; }
                        warp_arrive(BAR(B_PUB + 7));
                    }
                    if (s > 0) { WG_WAIT(1); warp_arrive(BAR(B_EMPTY + s - 1)); }
                }
                WG_WAIT(0);
                reg_fence<32>(ac);
                __syncwarp();
                if (lane < 6) mbar_arrive(BAR(B_EMPTY + 6 + lane));
                PROFC(20);
#pragma unroll
                for (int g = 0; g < 4; g++) {
                    h2b[16 + 2 * g] = hmul2(pack2_relu(ac[4 * g], ac[4 * g + 1]), pack2(ac[16 + 4 * g], ac[16 + 4 * g + 1]));
                    h2b[16 + 2 * g + 1] = hmul2(pack2_relu(ac[4 * g + 2], ac[4 * g + 3]), pack2(ac[16 + 4 * g + 2], ac[16 + 4 * g + 3]));
                    h2g[(fc / 8 + g) * 512] = h2b[16 + 2 * g]; h2g[(fc / 8 + g) * 512 + 32] = h2b[16 + 2 * g + 1];
                }
                warp_arrive(BAR(B_PUB + 8));
                asm volatile("barrier.cluster.wait.aligned;" ::: "memory");
                if (lane == 0 && !sc) {
                    uint32_t rb;
                    asm volatile("mapa.shared::cluster.u32 %0, %1, %2;" : "=r"(rb) : "r"(BAR(B_PEER)), "r"(kh ^ 1));
                    asm volatile("mbarrier.arrive.relaxed.cluster.shared::cluster.b64 _, [%0];" ::"r"(rb) : "memory");
                }
            } else reg_def<8>(h2b + 16);
        }
        PROFC(21);
        if (RUN(7)) {
            float ac[56];
            reg_def<56>(ac);
            constexpr uint64_t DAN = dconst(2048, 128, 0);
            constexpr uint64_t DW = dconst(128, 512, 0);
            const uint32_t bx = mkdesc(sb, DW);
#pragma unroll
            for (int e = 0; e < 4; e++) {
                WAIT(B_FULL + e, 0);
                const uint64_t bd = ((DW & ~0xFFFFFFFFull) | bx) + (slot_off(e) >> 4);
                const uint32_t* hh = e < 2 ? h2a + 16 * e : h2b + 16 * (e - 2);
                WG_FENCE();
#pragma unroll
                for (int k = 0; k < (e < 3 ? 4 : 2); k++) wgmma_rl_112(ac, hh[4 * k], hh[4 * k + 1], hh[4 * k + 2], hh[4 * k + 3], bd + (k >> 1) * 512 + (k & 1) * 16, (e | k) != 0);
                WG_COMMIT();
                if (e > 0) { WG_WAIT(1); warp_arrive(BAR(B_EMPTY + e - 1)); }
            }
            PROFC(22);
            uint32_t ad = mkdesc(sb + 4 * 16384 + 8192 + w * 1024, DAN), bd = bx + 4 * 1024, fb_ = BAR(B_FULL + 4), eb_ = BAR(B_EMPTY + 3), par = sc;
#pragma unroll 1
            for (int e = 4; e < 25; e++) {
                mbar_wait_c(fb_, par);
                WG_FENCE();
                wgmma_ss_112<DAN, DW>(ac, ad, bd, 1);
                wgmma_ss_112<DAN, DW>(ac, ad + 256, bd + 16, 1);
                WG_COMMIT();
                WG_WAIT(1);
                warp_arrive(eb_);
                eb_ = fb_ + 8 * (B_EMPTY - B_FULL);
                ad += 1024; bd += 1024; fb_ += 8;
                if (e == 11 || e == 23) { ad -= 12 * 1024; bd -= 12 * 1024; fb_ -= 96; par = (par ^ 1) | sc; }
            }
            mbar_wait_cluster(BAR(B_PEER), sc);
            WG_WAIT(0);
            reg_fence<56>(ac);
            PROFC(24);
            uint32_t rdst, rbar;
            asm volatile("mapa.shared::cluster.u32 %0, %1, %2;" : "=r"(rdst) : "r"(sb + OFF_Y + (5 + w) * 16384 + t * 16), "r"(kh ^ 1 ^ sc));
            asm volatile("mapa.shared::cluster.u32 %0, %1, %2;" : "=r"(rbar) : "r"(BAR(B_XCH + w)), "r"(kh ^ 1 ^ sc));
#pragma unroll
            for (int g = 0; g < 7; g++) {
                const float v0 = ac[28 + 4 * g + 0], v1 = ac[28 + 4 * g + 1];
                const float v2 = ac[28 + 4 * g + 2], v3 = ac[28 + 4 * g + 3];
                if (!sc) asm volatile("st.async.shared::cluster.mbarrier::complete_tx::bytes.v4.f32 [%0], {%1,%2,%3,%4}, [%5];"
                             ::"r"(rdst + g * 2048), "f"(v0), "f"(v1), "f"(v2), "f"(v3), "r"(rbar) : "memory");
            }
            mbar_wait_cluster(BAR(B_XCH + w), sc);
            PROFC(25);
            uint32_t op[16];
#pragma unroll
            for (int g = 0; g < 7; g++) {
                const uint4 rv = *(const uint4*)(smem + OFF_Y + (5 + w) * 16384 + t * 16 + g * 2048);
                const float2 gb = *(const float2*)(smem + M_G + 224 + (8 * g + 2 * q) * 4);
                const float v0 = ac[4 * g + 0] + __uint_as_float(rv.x), v1 = ac[4 * g + 1] + __uint_as_float(rv.y);
                const float v2 = ac[4 * g + 2] + __uint_as_float(rv.z), v3 = ac[4 * g + 3] + __uint_as_float(rv.w);
                op[2 * g] = pack2(fmaf(gb.x, v0, bf_lo(x1p[2 * g])), fmaf(gb.y, v1, bf_hi(x1p[2 * g])));
                op[2 * g + 1] = pack2(fmaf(gb.x, v2, bf_lo(x1p[2 * g + 1])), fmaf(gb.y, v3, bf_hi(x1p[2 * g + 1])));
            }
            WAIT(B_EMPTY + 1, 0);
            const uint32_t oc = sb + OUT_STAGE + warp * 1792;
            const uint32_t oa = oc + (((lane >> 3) & 1) * 8 + (lane & 7)) * 112 + (lane >> 4) * 16;
            stsm4(oa, op[0], op[1], op[2], op[3]); stsm4(oa + 32, op[4], op[5], op[6], op[7]); stsm4(oa + 64, op[8], op[9], op[10], op[11]);
            asm volatile("stmatrix.sync.aligned.m8n8.x2.shared.b16 [%0], {%1,%2};" ::"r"(oa + 96), "r"(op[12]), "r"(op[13]));
            fence_async_smem();
            __syncwarp();
            asm volatile("{\n.reg .pred p;\nelect.sync _|p, 0xffffffff;\n@p cp.async.bulk.tensor.3d.global.shared::cta.bulk_group [%0, {%2, %3, %4}], [%1];\n"
                         "cp.async.bulk.commit_group;\ncp.async.bulk.wait_group.read 0;\n}" ::"l"(&p.om), "r"(oc), "r"(56 * j), "r"(128 * r + 16 * warp), "r"(0) : "memory");
        }
        PROFC(26);
        bar_sync(1 + w, 128);
        if (wi == 0) warp_arrive(BAR(B_DONE));
        return;
    }
    helper_late(p, r, j, warp PROF_ARGS);
}

#undef act
typedef CUresult (*EncodeFn)(CUtensorMap*, CUtensorMapDataType, cuuint32_t, void*, const cuuint64_t*, const cuuint64_t*, const cuuint32_t*,
                             const cuuint32_t*, CUtensorMapInterleave, CUtensorMapSwizzle, CUtensorMapL2promotion, CUtensorMapFloatOOBfill);

static void make_map(EncodeFn fn, CUtensorMap* m, const void* ptr, uint64_t d0, uint64_t d1, uint64_t d2, uint64_t s1, uint64_t s2,
                     uint32_t b0, uint32_t b1, uint32_t b2, CUtensorMapSwizzle sw) {
    cuuint64_t dims[3] = {d0, d1, d2}, strides[2] = {s1, s2};
    cuuint32_t box[3] = {b0, b1, b2}, es[3] = {1, 1, 1};
    CUresult rc = fn(m, CU_TENSOR_MAP_DATA_TYPE_BFLOAT16, 3, (void*)ptr, dims, strides, box, es, CU_TENSOR_MAP_INTERLEAVE_NONE, sw,
                     CU_TENSOR_MAP_L2_PROMOTION_L2_128B, CU_TENSOR_MAP_FLOAT_OOB_FILL_NONE);
    (void)rc;
}

extern "C" void kernel_launch(void* const* d_in, const int* in_sizes, int n_in, void* d_out, int out_size) {
    (void)in_sizes; (void)n_in; (void)out_size;
    static EncodeFn fn = nullptr;
    static uint32_t* act_base = nullptr;
    if (!fn) {
        cudaDriverEntryPointQueryResult st;
        cudaGetDriverEntryPoint("cuTensorMapEncodeTiled", (void**)&fn, cudaEnableDefault, &st);
        void* a = nullptr;
        cudaGetSymbolAddress(&a, g_act);
        act_base = (uint32_t*)(((uintptr_t)a + 0xFFFFF) & ~(uintptr_t)0xFFFFF);
        cudaFuncSetAttribute(fused_block_kernel, cudaFuncAttributeMaxDynamicSharedMemorySize, SMEM_BYTES);
    }
    Params p;
    p.x = (const bf16*)d_in[0];
    const bf16* wqkv = (const bf16*)d_in[1];
    p.wqkv = wqkv;
    p.wop = (const bf16*)d_in[2];
    p.wg = (const bf16*)d_in[4];
    p.wu = (const bf16*)d_in[5];
    p.wd = (const bf16*)d_in[6];
    p.c = (const bf16*)d_in[7];
    p.wmod = (const bf16*)d_in[8];
    p.out = (bf16*)d_out;
    p.zero = 0;
    p.actb = act_base;
    make_map(fn, &p.wm, p.wmod, 2688, 448, 1, 5376, 5376 * 448, 16, 224, 1, CU_TENSOR_MAP_SWIZZLE_NONE);
    make_map(fn, &p.wm2, p.wmod, 2688, 448, 1, 5376, 5376 * 448, 32, 224, 1, CU_TENSOR_MAP_SWIZZLE_NONE);
    make_map(fn, &p.om, p.out, 448, 2048, 1, 896, 896 * 2048, 56, 16, 1, CU_TENSOR_MAP_SWIZZLE_NONE);
    make_map(fn, &p.xm, p.x, 448, 2048, 1, 896, 896 * 2048, 64, 128, 1, CU_TENSOR_MAP_SWIZZLE_128B);
    make_map(fn, &p.qkv, wqkv, 1344, 448, 1, 2688, 2688 * 448, 64, 224, 1, CU_TENSOR_MAP_SWIZZLE_128B);
    make_map(fn, &p.wo, p.wop, 448, 448, 1, 896, 896 * 448, 64, 224, 1, CU_TENSOR_MAP_SWIZZLE_128B);
    make_map(fn, &p.ga, p.wg, 64, 448, 28, 3584, 128, 64, 32, 2, CU_TENSOR_MAP_SWIZZLE_128B);
    make_map(fn, &p.ua, p.wu, 64, 448, 28, 3584, 128, 64, 32, 2, CU_TENSOR_MAP_SWIZZLE_128B);
    make_map(fn, &p.gb, p.wg, 64, 448, 28, 3584, 128, 64, 64, 1, CU_TENSOR_MAP_SWIZZLE_128B);
    make_map(fn, &p.ub, p.wu, 64, 448, 28, 3584, 128, 64, 64, 1, CU_TENSOR_MAP_SWIZZLE_128B);
    make_map(fn, &p.gc, p.wg, 32, 448, 56, 3584, 64, 32, 64, 1, CU_TENSOR_MAP_SWIZZLE_64B);
    make_map(fn, &p.uc, p.wu, 32, 448, 56, 3584, 64, 32, 64, 1, CU_TENSOR_MAP_SWIZZLE_64B);
    make_map(fn, &p.dn, p.wd, 8, 1792, 56, 896, 16, 8, 32, 7, CU_TENSOR_MAP_SWIZZLE_NONE);
    fused_block_kernel<<<GRID, 384, SMEM_BYTES>>>(p);
}
```

```cpp
#include <cuda_runtime.h>
#include <cuda_bf16.h>
#include <cuda.h>
#include <stdint.h>

typedef __nv_bfloat16 bf16;

template<uint64_t CA, uint64_t CB> __device__ __forceinline__ void wgmma_sk_160(float* d, uint32_t da, uint32_t db, int sd) {
  asm volatile("{\n.reg .pred p;\n.reg .b64 a, b;\nsetp.ne.b32 p, %82, 0;\nmov.b64 a, {%80, %83};\nmov.b64 b, {%81, %84};\n"
    "wgmma.mma_async.sync.aligned.m64n160k16.f32.bf16.bf16 {%0,%1,%2,%3,%4,%5,%6,%7,%8,%9,%10,%11,%12,%13,%14,%15,%16,%17,%18,%19,%20,%21,%22,%23,%24,%25,%26,%27,%28,%29,%30,%31,%32,%33,%34,%35,%36,%37,%38,%39,%40,%41,%42,%43,%44,%45,%46,%47,%48,%49,%50,%51,%52,%53,%54,%55,%56,%57,%58,%59,%60,%61,%62,%63,%64,%65,%66,%67,%68,%69,%70,%71,%72,%73,%74,%75,%76,%77,%78,%79}, a, b, p, 1, 1, 0, 0;\n}\n"
    : "+f"(d[0]),"+f"(d[1]),"+f"(d[2]),"+f"(d[3]),"+f"(d[4]),"+f"(d[5]),"+f"(d[6]),"+f"(d[7]),"+f"(d[8]),"+f"(d[9]),"+f"(d[10]),"+f"(d[11]),"+f"(d[12]),"+f"(d[13]),"+f"(d[14]),"+f"(d[15]),"+f"(d[16]),"+f"(d[17]),"+f"(d[18]),"+f"(d[19]),"+f"(d[20]),"+f"(d[21]),"+f"(d[22]),"+f"(d[23]),"+f"(d[24]),"+f"(d[25]),"+f"(d[26]),"+f"(d[27]),"+f"(d[28]),"+f"(d[29]),"+f"(d[30]),"+f"(d[31]),"+f"(d[32]),"+f"(d[33]),"+f"(d[34]),"+f"(d[35]),"+f"(d[36]),"+f"(d[37]),"+f"(d[38]),"+f"(d[39]),"+f"(d[40]),"+f"(d[41]),"+f"(d[42]),"+f"(d[43]),"+f"(d[44]),"+f"(d[45]),"+f"(d[46]),"+f"(d[47]),"+f"(d[48]),"+f"(d[49]),"+f"(d[50]),"+f"(d[51]),"+f"(d[52]),"+f"(d[53]),"+f"(d[54]),"+f"(d[55]),"+f"(d[56]),"+f"(d[57]),"+f"(d[58]),"+f"(d[59]),"+f"(d[60]),"+f"(d[61]),"+f"(d[62]),"+f"(d[63]),"+f"(d[64]),"+f"(d[65]),"+f"(d[66]),"+f"(d[67]),"+f"(d[68]),"+f"(d[69]),"+f"(d[70]),"+f"(d[71]),"+f"(d[72]),"+f"(d[73]),"+f"(d[74]),"+f"(d[75]),"+f"(d[76]),"+f"(d[77]),"+f"(d[78]),"+f"(d[79])
    : "r"(da), "r"(db), "r"(sd), "n"((uint32_t)(CA >> 32)), "n"((uint32_t)(CB >> 32)));
}
__device__ __forceinline__ void wgmma_rl_56(float* d, uint32_t a0, uint32_t a1, uint32_t a2, uint32_t a3, uint64_t db, int sd) {
  asm volatile("{\n.reg .pred p;\nsetp.ne.b32 p, %33, 0;\n"
    "wgmma.mma_async.sync.aligned.m64n56k16.f32.bf16.bf16 {%0,%1,%2,%3,%4,%5,%6,%7,%8,%9,%10,%11,%12,%13,%14,%15,%16,%17,%18,%19,%20,%21,%22,%23,%24,%25,%26,%27}, {%28,%29,%30,%31}, %32, p, 1, 1, 1;\n}\n"
    : "+f"(d[0]),"+f"(d[1]),"+f"(d[2]),"+f"(d[3]),"+f"(d[4]),"+f"(d[5]),"+f"(d[6]),"+f"(d[7]),"+f"(d[8]),"+f"(d[9]),"+f"(d[10]),"+f"(d[11]),"+f"(d[12]),"+f"(d[13]),"+f"(d[14]),"+f"(d[15]),"+f"(d[16]),"+f"(d[17]),"+f"(d[18]),"+f"(d[19]),"+f"(d[20]),"+f"(d[21]),"+f"(d[22]),"+f"(d[23]),"+f"(d[24]),"+f"(d[25]),"+f"(d[26]),"+f"(d[27])
    : "r"(a0), "r"(a1), "r"(a2), "r"(a3), "l"(db), "r"(sd));
}
template<uint64_t CA, uint64_t CB> __device__ __forceinline__ void wgmma_ss_56(float* d, uint32_t da, uint32_t db, int sd) {
  asm volatile("{\n.reg .pred p;\n.reg .b64 a, b;\nsetp.ne.b32 p, %30, 0;\nmov.b64 a, {%28, %31};\nmov.b64 b, {%29, %32};\n"
    "wgmma.mma_async.sync.aligned.m64n56k16.f32.bf16.bf16 {%0,%1,%2,%3,%4,%5,%6,%7,%8,%9,%10,%11,%12,%13,%14,%15,%16,%17,%18,%19,%20,%21,%22,%23,%24,%25,%26,%27}, a, b, p, 1, 1, 0, 1;\n}\n"
    : "+f"(d[0]),"+f"(d[1]),"+f"(d[2]),"+f"(d[3]),"+f"(d[4]),"+f"(d[5]),"+f"(d[6]),"+f"(d[7]),"+f"(d[8]),"+f"(d[9]),"+f"(d[10]),"+f"(d[11]),"+f"(d[12]),"+f"(d[13]),"+f"(d[14]),"+f"(d[15]),"+f"(d[16]),"+f"(d[17]),"+f"(d[18]),"+f"(d[19]),"+f"(d[20]),"+f"(d[21]),"+f"(d[22]),"+f"(d[23]),"+f"(d[24]),"+f"(d[25]),"+f"(d[26]),"+f"(d[27])
    : "r"(da), "r"(db), "r"(sd), "n"((uint32_t)(CA >> 32)), "n"((uint32_t)(CB >> 32)));
}
__device__ __forceinline__ void wgmma_rl_256(float* d, uint32_t a0, uint32_t a1, uint32_t a2, uint32_t a3, uint64_t db, int sd) {
  asm volatile("{\n.reg .pred p;\nsetp.ne.b32 p, %133, 0;\n"
    "wgmma.mma_async.sync.aligned.m64n256k16.f32.bf16.bf16 {%0,%1,%2,%3,%4,%5,%6,%7,%8,%9,%10,%11,%12,%13,%14,%15,%16,%17,%18,%19,%20,%21,%22,%23,%24,%25,%26,%27,%28,%29,%30,%31,%32,%33,%34,%35,%36,%37,%38,%39,%40,%41,%42,%43,%44,%45,%46,%47,%48,%49,%50,%51,%52,%53,%54,%55,%56,%57,%58,%59,%60,%61,%62,%63,%64,%65,%66,%67,%68,%69,%70,%71,%72,%73,%74,%75,%76,%77,%78,%79,%80,%81,%82,%83,%84,%85,%86,%87,%88,%89,%90,%91,%92,%93,%94,%95,%96,%97,%98,%99,%100,%101,%102,%103,%104,%105,%106,%107,%108,%109,%110,%111,%112,%113,%114,%115,%116,%117,%118,%119,%120,%121,%122,%123,%124,%125,%126,%127}, {%128,%129,%130,%131}, %132, p, 1, 1, 1;\n}\n"
    : "+f"(d[0]),"+f"(d[1]),"+f"(d[2]),"+f"(d[3]),"+f"(d[4]),"+f"(d[5]),"+f"(d[6]),"+f"(d[7]),"+f"(d[8]),"+f"(d[9]),"+f"(d[10]),"+f"(d[11]),"+f"(d[12]),"+f"(d[13]),"+f"(d[14]),"+f"(d[15]),"+f"(d[16]),"+f"(d[17]),"+f"(d[18]),"+f"(d[19]),"+f"(d[20]),"+f"(d[21]),"+f"(d[22]),"+f"(d[23]),"+f"(d[24]),"+f"(d[25]),"+f"(d[26]),"+f"(d[27]),"+f"(d[28]),"+f"(d[29]),"+f"(d[30]),"+f"(d[31]),"+f"(d[32]),"+f"(d[33]),"+f"(d[34]),"+f"(d[35]),"+f"(d[36]),"+f"(d[37]),"+f"(d[38]),"+f"(d[39]),"+f"(d[40]),"+f"(d[41]),"+f"(d[42]),"+f"(d[43]),"+f"(d[44]),"+f"(d[45]),"+f"(d[46]),"+f"(d[47]),"+f"(d[48]),"+f"(d[49]),"+f"(d[50]),"+f"(d[51]),"+f"(d[52]),"+f"(d[53]),"+f"(d[54]),"+f"(d[55]),"+f"(d[56]),"+f"(d[57]),"+f"(d[58]),"+f"(d[59]),"+f"(d[60]),"+f"(d[61]),"+f"(d[62]),"+f"(d[63]),"+f"(d[64]),"+f"(d[65]),"+f"(d[66]),"+f"(d[67]),"+f"(d[68]),"+f"(d[69]),"+f"(d[70]),"+f"(d[71]),"+f"(d[72]),"+f"(d[73]),"+f"(d[74]),"+f"(d[75]),"+f"(d[76]),"+f"(d[77]),"+f"(d[78]),"+f"(d[79]),"+f"(d[80]),"+f"(d[81]),"+f"(d[82]),"+f"(d[83]),"+f"(d[84]),"+f"(d[85]),"+f"(d[86]),"+f"(d[87]),"+f"(d[88]),"+f"(d[89]),"+f"(d[90]),"+f"(d[91]),"+f"(d[92]),"+f"(d[93]),"+f"(d[94]),"+f"(d[95]),"+f"(d[96]),"+f"(d[97]),"+f"(d[98]),"+f"(d[99]),"+f"(d[100]),"+f"(d[101]),"+f"(d[102]),"+f"(d[103]),"+f"(d[104]),"+f"(d[105]),"+f"(d[106]),"+f"(d[107]),"+f"(d[108]),"+f"(d[109]),"+f"(d[110]),"+f"(d[111]),"+f"(d[112]),"+f"(d[113]),"+f"(d[114]),"+f"(d[115]),"+f"(d[116]),"+f"(d[117]),"+f"(d[118]),"+f"(d[119]),"+f"(d[120]),"+f"(d[121]),"+f"(d[122]),"+f"(d[123]),"+f"(d[124]),"+f"(d[125]),"+f"(d[126]),"+f"(d[127])
    : "r"(a0), "r"(a1), "r"(a2), "r"(a3), "l"(db), "r"(sd));
}
template<uint64_t CA, uint64_t CB> __device__ __forceinline__ void wgmma_ss_128(float* d, uint32_t da, uint32_t db, int sd) {
  asm volatile("{\n.reg .pred p;\n.reg .b64 a, b;\nsetp.ne.b32 p, %66, 0;\nmov.b64 a, {%64, %67};\nmov.b64 b, {%65, %68};\n"
    "wgmma.mma_async.sync.aligned.m64n128k16.f32.bf16.bf16 {%0,%1,%2,%3,%4,%5,%6,%7,%8,%9,%10,%11,%12,%13,%14,%15,%16,%17,%18,%19,%20,%21,%22,%23,%24,%25,%26,%27,%28,%29,%30,%31,%32,%33,%34,%35,%36,%37,%38,%39,%40,%41,%42,%43,%44,%45,%46,%47,%48,%49,%50,%51,%52,%53,%54,%55,%56,%57,%58,%59,%60,%61,%62,%63}, a, b, p, 1, 1, 0, 1;\n}\n"
    : "+f"(d[0]),"+f"(d[1]),"+f"(d[2]),"+f"(d[3]),"+f"(d[4]),"+f"(d[5]),"+f"(d[6]),"+f"(d[7]),"+f"(d[8]),"+f"(d[9]),"+f"(d[10]),"+f"(d[11]),"+f"(d[12]),"+f"(d[13]),"+f"(d[14]),"+f"(d[15]),"+f"(d[16]),"+f"(d[17]),"+f"(d[18]),"+f"(d[19]),"+f"(d[20]),"+f"(d[21]),"+f"(d[22]),"+f"(d[23]),"+f"(d[24]),"+f"(d[25]),"+f"(d[26]),"+f"(d[27]),"+f"(d[28]),"+f"(d[29]),"+f"(d[30]),"+f"(d[31]),"+f"(d[32]),"+f"(d[33]),"+f"(d[34]),"+f"(d[35]),"+f"(d[36]),"+f"(d[37]),"+f"(d[38]),"+f"(d[39]),"+f"(d[40]),"+f"(d[41]),"+f"(d[42]),"+f"(d[43]),"+f"(d[44]),"+f"(d[45]),"+f"(d[46]),"+f"(d[47]),"+f"(d[48]),"+f"(d[49]),"+f"(d[50]),"+f"(d[51]),"+f"(d[52]),"+f"(d[53]),"+f"(d[54]),"+f"(d[55]),"+f"(d[56]),"+f"(d[57]),"+f"(d[58]),"+f"(d[59]),"+f"(d[60]),"+f"(d[61]),"+f"(d[62]),"+f"(d[63])
    : "r"(da), "r"(db), "r"(sd), "n"((uint32_t)(CA >> 32)), "n"((uint32_t)(CB >> 32)));
}
template<uint64_t CA, uint64_t CB> __device__ __forceinline__ void wgmma_ss_64(float* d, uint32_t da, uint32_t db, int sd) {
  asm volatile("{\n.reg .pred p;\n.reg .b64 a, b;\nsetp.ne.b32 p, %34, 0;\nmov.b64 a, {%32, %35};\nmov.b64 b, {%33, %36};\n"
    "wgmma.mma_async.sync.aligned.m64n64k16.f32.bf16.bf16 {%0,%1,%2,%3,%4,%5,%6,%7,%8,%9,%10,%11,%12,%13,%14,%15,%16,%17,%18,%19,%20,%21,%22,%23,%24,%25,%26,%27,%28,%29,%30,%31}, a, b, p, 1, 1, 0, 1;\n}\n"
    : "+f"(d[0]),"+f"(d[1]),"+f"(d[2]),"+f"(d[3]),"+f"(d[4]),"+f"(d[5]),"+f"(d[6]),"+f"(d[7]),"+f"(d[8]),"+f"(d[9]),"+f"(d[10]),"+f"(d[11]),"+f"(d[12]),"+f"(d[13]),"+f"(d[14]),"+f"(d[15]),"+f"(d[16]),"+f"(d[17]),"+f"(d[18]),"+f"(d[19]),"+f"(d[20]),"+f"(d[21]),"+f"(d[22]),"+f"(d[23]),"+f"(d[24]),"+f"(d[25]),"+f"(d[26]),"+f"(d[27]),"+f"(d[28]),"+f"(d[29]),"+f"(d[30]),"+f"(d[31])
    : "r"(da), "r"(db), "r"(sd), "n"((uint32_t)(CA >> 32)), "n"((uint32_t)(CB >> 32)));
}
template<uint64_t CA, uint64_t CB> __device__ __forceinline__ void wgmma_ss_112(float* d, uint32_t da, uint32_t db, int sd) {
  asm volatile("{\n.reg .pred p;\n.reg .b64 a, b;\nsetp.ne.b32 p, %58, 0;\nmov.b64 a, {%56, %59};\nmov.b64 b, {%57, %60};\n"
    "wgmma.mma_async.sync.aligned.m64n112k16.f32.bf16.bf16 {%0,%1,%2,%3,%4,%5,%6,%7,%8,%9,%10,%11,%12,%13,%14,%15,%16,%17,%18,%19,%20,%21,%22,%23,%24,%25,%26,%27,%28,%29,%30,%31,%32,%33,%34,%35,%36,%37,%38,%39,%40,%41,%42,%43,%44,%45,%46,%47,%48,%49,%50,%51,%52,%53,%54,%55}, a, b, p, 1, 1, 0, 1;\n}\n"
    : "+f"(d[0]),"+f"(d[1]),"+f"(d[2]),"+f"(d[3]),"+f"(d[4]),"+f"(d[5]),"+f"(d[6]),"+f"(d[7]),"+f"(d[8]),"+f"(d[9]),"+f"(d[10]),"+f"(d[11]),"+f"(d[12]),"+f"(d[13]),"+f"(d[14]),"+f"(d[15]),"+f"(d[16]),"+f"(d[17]),"+f"(d[18]),"+f"(d[19]),"+f"(d[20]),"+f"(d[21]),"+f"(d[22]),"+f"(d[23]),"+f"(d[24]),"+f"(d[25]),"+f"(d[26]),"+f"(d[27]),"+f"(d[28]),"+f"(d[29]),"+f"(d[30]),"+f"(d[31]),"+f"(d[32]),"+f"(d[33]),"+f"(d[34]),"+f"(d[35]),"+f"(d[36]),"+f"(d[37]),"+f"(d[38]),"+f"(d[39]),"+f"(d[40]),"+f"(d[41]),"+f"(d[42]),"+f"(d[43]),"+f"(d[44]),"+f"(d[45]),"+f"(d[46]),"+f"(d[47]),"+f"(d[48]),"+f"(d[49]),"+f"(d[50]),"+f"(d[51]),"+f"(d[52]),"+f"(d[53]),"+f"(d[54]),"+f"(d[55])
    : "r"(da), "r"(db), "r"(sd), "n"((uint32_t)(CA >> 32)), "n"((uint32_t)(CB >> 32)));
}
__device__ __forceinline__ void wgmma_rl_112(float* d, uint32_t a0, uint32_t a1, uint32_t a2, uint32_t a3, uint64_t db, int sd) {
  asm volatile("{\n.reg .pred p;\nsetp.ne.b32 p, %61, 0;\n"
    "wgmma.mma_async.sync.aligned.m64n112k16.f32.bf16.bf16 {%0,%1,%2,%3,%4,%5,%6,%7,%8,%9,%10,%11,%12,%13,%14,%15,%16,%17,%18,%19,%20,%21,%22,%23,%24,%25,%26,%27,%28,%29,%30,%31,%32,%33,%34,%35,%36,%37,%38,%39,%40,%41,%42,%43,%44,%45,%46,%47,%48,%49,%50,%51,%52,%53,%54,%55}, {%56,%57,%58,%59}, %60, p, 1, 1, 1;\n}\n"
    : "+f"(d[0]),"+f"(d[1]),"+f"(d[2]),"+f"(d[3]),"+f"(d[4]),"+f"(d[5]),"+f"(d[6]),"+f"(d[7]),"+f"(d[8]),"+f"(d[9]),"+f"(d[10]),"+f"(d[11]),"+f"(d[12]),"+f"(d[13]),"+f"(d[14]),"+f"(d[15]),"+f"(d[16]),"+f"(d[17]),"+f"(d[18]),"+f"(d[19]),"+f"(d[20]),"+f"(d[21]),"+f"(d[22]),"+f"(d[23]),"+f"(d[24]),"+f"(d[25]),"+f"(d[26]),"+f"(d[27]),"+f"(d[28]),"+f"(d[29]),"+f"(d[30]),"+f"(d[31]),"+f"(d[32]),"+f"(d[33]),"+f"(d[34]),"+f"(d[35]),"+f"(d[36]),"+f"(d[37]),"+f"(d[38]),"+f"(d[39]),"+f"(d[40]),"+f"(d[41]),"+f"(d[42]),"+f"(d[43]),"+f"(d[44]),"+f"(d[45]),"+f"(d[46]),"+f"(d[47]),"+f"(d[48]),"+f"(d[49]),"+f"(d[50]),"+f"(d[51]),"+f"(d[52]),"+f"(d[53]),"+f"(d[54]),"+f"(d[55])
    : "r"(a0), "r"(a1), "r"(a2), "r"(a3), "l"(db), "r"(sd));
}

constexpr int DM = 448;
constexpr int NCTA = 128;
#define MAPPING 1
#define GRID 128
#define PINGPONG 0
#define WIN 6
#define WIN_END 25
#define UNR_B 1
#define UNR_C 1
constexpr int kB = UNR_B, kC = UNR_C;
#define LIKELY(x) __builtin_expect(!!(x), 1)
#define PACE 1
#define PACE_END 6
#define GEMV_AT 0
#define NPRE 14
#define ATT_OFF 0
#define ATT_WG 1
#define XFIRST 7
#define KDELAY 0
#define KEARLY 1
#define VPRE 3
#define VGATE 2
#define LNMODE 0
#define WSWAP 1
#define ASYM 1
#define MAP_S 4
constexpr int SPIN_LIMIT = 1 << 22;

constexpr uint32_t OFF_X = 0, OFF_Y = 114688, OFF_MISC = 229376, SMEM_BYTES = 232448;
constexpr uint32_t Y_VR = 0, Y_K = 28672, Y_KOWN = 57344, Y_VOWN = 71680, Y_Q = 86016;
constexpr uint32_t HALF = 57344;
constexpr uint32_t X_STAT = 49152;
constexpr uint32_t OUT_STAGE = 16384;
constexpr uint32_t M_BAR = OFF_MISC;
constexpr uint32_t M_ST = OFF_MISC + 512;
constexpr uint32_t M_G = OFF_MISC + 2304;
constexpr uint32_t M_EPOCH = OFF_MISC + 3040;
enum { B_XFULL = 0, B_FULLK = 7, B_FULLV = 8, B_FULLQ, B_KRFULL, B_VRFULL, B_WOFULL, B_XCH, B_MOD1 = 15, B_FULL = 16, B_WMFULL = 30,
       B_EMPTY = 32, B_XFREE = B_EMPTY + 12, B_GEMV, B_PEER,
       B_PUB = 47,
       B_WMFREE = 56, B_HRDY, B_GFULL = B_HRDY + 3, B_DONE = 31, B_DUMMY = B_GEMV };

__device__ uint32_t g_ticket;
__device__ __align__(128) uint32_t g_mod[8 * 6 * DM];
__device__ __align__(128) uint32_t g_flag[144 * 128];
constexpr int RB_WORDS = 262144, RB_KV = 0, RB_O = 57344, RB_X1 = 86016, RB_H2 = 143360, RB_ST = 258048;
__device__ __align__(128) uint32_t g_act[18 * RB_WORDS];
__device__ __align__(128) uint32_t g_wd[56 * 4 * 1792];
#define PROFH(id)
#define PROFH1(id)
#define PROFC(id)

struct alignas(64) Params {
    CUtensorMap wm, wm2, om, xm, qkv, wo, ga, ua, gb, ub, gc, uc, dn;
    const bf16 *x, *c, *wqkv, *wmod, *wg, *wu, *wd, *wop;
    bf16* out;
    uint32_t* actb;
    uint32_t zero;
};

__device__ __forceinline__ void mbar_init(uint32_t bar, int cnt) { asm volatile("mbarrier.init.shared::cta.b64 [%0], %1;" ::"r"(bar), "r"(cnt) : "memory"); }
__device__ __forceinline__ void mbar_expect_tx(uint32_t bar, uint32_t bytes) { asm volatile("mbarrier.arrive.expect_tx.shared::cta.b64 _, [%0], %1;" ::"r"(bar), "r"(bytes) : "memory"); }
__device__ __forceinline__ void mbar_arrive(uint32_t bar) { asm volatile("mbarrier.arrive.shared::cta.b64 _, [%0];" ::"r"(bar) : "memory"); }
__device__ __forceinline__ void mbar_wait(uint32_t bar, uint32_t parity) {
    uint32_t ok; int n = 0;
    do {
        asm volatile("{\n.reg .pred p;\nmbarrier.try_wait.parity.shared::cta.b64 p, [%1], %2;\nselp.u32 %0, 1, 0, p;\n}" : "=r"(ok) : "r"(bar), "r"(parity) : "memory");
        if (++n > SPIN_LIMIT) __trap();
    } while (!ok);
}
__device__ __forceinline__ void mbar_wait_c(uint32_t bar, uint32_t parity) {
    asm volatile("{\n.reg .pred p;\nWL:\nmbarrier.try_wait.parity.shared::cta.b64 p, [%0], %1, 0x989680;\n@!p bra WL;\n}" ::"r"(bar), "r"(parity) : "memory");
}
__device__ __forceinline__ void mbar_wait_cluster(uint32_t bar, uint32_t parity) {
    asm volatile("{\n.reg .pred p;\nWL:\nmbarrier.try_wait.parity.acquire.cluster.shared::cta.b64 p, [%0], %1, 0x989680;\n@!p bra WL;\n}" ::"r"(bar), "r"(parity) : "memory");
}
__device__ __forceinline__ void warp_arrive(uint32_t bar) {
    __syncwarp();
    asm volatile("{\n.reg .pred p;\nelect.sync _|p, 0xffffffff;\n@p mbarrier.arrive.shared::cta.b64 _, [%0];\n}" ::"r"(bar) : "memory");
}
__device__ __forceinline__ int opaque(int v) { return __shfl_sync(~0u, v, 0); }
__device__ __forceinline__ int fresh_tid() { int v; asm volatile("mov.u32 %0, %%tid.x;" : "=r"(v)); return v; }
__device__ __forceinline__ void bar_sync(int id, int n) { asm volatile("bar.sync %0, %1;" ::"r"(id), "r"(n) : "memory"); }
__device__ __forceinline__ void bar_arrive(int id, int n) { asm volatile("bar.arrive %0, %1;" ::"r"(id), "r"(n) : "memory"); }
__device__ __forceinline__ void fence_async_smem() { asm volatile("fence.proxy.async.shared::cta;" ::: "memory"); }
__device__ __forceinline__ void fence_async_global() { asm volatile("fence.proxy.async.global;" ::: "memory"); }
__device__ __forceinline__ void fence_gpu() { asm volatile("fence.release.gpu;" ::: "memory"); }
__device__ __forceinline__ void tma3(uint32_t dst, const CUtensorMap* m, int c0, int c1, int c2, uint32_t bar) {
    asm volatile("cp.async.bulk.tensor.3d.shared::cluster.global.mbarrier::complete_tx::bytes [%0], [%1, {%3, %4, %5}], [%2];"
                 ::"r"(dst), "l"(m), "r"(bar), "r"(c0), "r"(c1), "r"(c2) : "memory");
}
__device__ __forceinline__ void bulk_load(uint32_t dst, const void* src, uint32_t bytes, uint32_t bar) {
    asm volatile("cp.async.bulk.shared::cluster.global.mbarrier::complete_tx::bytes [%0], [%1], %2, [%3];" ::"r"(dst), "l"(src), "r"(bytes), "r"(bar) : "memory");
}
__device__ __forceinline__ void expect_e(uint32_t bar, uint32_t bytes) {
    asm volatile("{\n.reg .pred p;\nelect.sync _|p, 0xffffffff;\n@p mbarrier.arrive.expect_tx.shared::cta.b64 _, [%0], %1;\n}" ::"r"(bar), "r"(bytes) : "memory");
}
__device__ __forceinline__ void tma3_e(uint32_t dst, const CUtensorMap* m, int c0, int c1, int c2, uint32_t bar) {
    asm volatile("{\n.reg .pred p;\nelect.sync _|p, 0xffffffff;\n@p cp.async.bulk.tensor.3d.shared::cluster.global.mbarrier::complete_tx::bytes [%0], [%1, {%3, %4, %5}], [%2];\n}"
                 ::"r"(dst), "l"(m), "r"(bar), "r"(c0), "r"(c1), "r"(c2) : "memory");
}
__device__ __forceinline__ void bulk_e(uint32_t dst, const void* src, uint32_t bytes, uint32_t bar) {
    asm volatile("{\n.reg .pred p;\nelect.sync _|p, 0xffffffff;\n@p cp.async.bulk.shared::cluster.global.mbarrier::complete_tx::bytes [%0], [%1], %2, [%3];\n}"
                 ::"r"(dst), "l"(src), "r"(bytes), "r"(bar) : "memory");
}
__device__ __forceinline__ void init_e(uint32_t bar, int cnt) {
    asm volatile("{\n.reg .pred p;\nelect.sync _|p, 0xffffffff;\n@p mbarrier.init.shared::cta.b64 [%0], %1;\n}" ::"r"(bar), "r"(cnt) : "memory");
}
__device__ __forceinline__ void l2_prefetch_e(const void* src, uint32_t bytes) {
    asm volatile("{\n.reg .pred p;\nelect.sync _|p, 0xffffffff;\n@p cp.async.bulk.prefetch.L2.global [%0], %1;\n}" ::"l"(src), "r"(bytes) : "memory");
}
__device__ __forceinline__ uint32_t ld_relaxed(const uint32_t* p) { uint32_t v; asm volatile("ld.relaxed.gpu.global.u32 %0, [%1];" : "=r"(v) : "l"(p) : "memory"); return v; }
__device__ __forceinline__ void st_relaxed(uint32_t* p, uint32_t v) { asm volatile("st.relaxed.gpu.global.u32 [%0], %1;" ::"l"(p), "r"(v) : "memory"); }
__device__ __forceinline__ uint4 ld_relaxed4(const uint4* p) { uint4 v; asm volatile("ld.relaxed.gpu.global.v4.u32 {%0,%1,%2,%3}, [%4];" : "=r"(v.x), "=r"(v.y), "=r"(v.z), "=r"(v.w) : "l"(p) : "memory"); return v; }
__device__ __forceinline__ void st_relaxed4(uint4* p, uint4 v) { asm volatile("st.relaxed.gpu.global.v4.u32 [%0], {%1,%2,%3,%4};" ::"l"(p), "r"(v.x), "r"(v.y), "r"(v.z), "r"(v.w) : "memory"); }
__device__ __forceinline__ uint4 ldg_nc4(const void* p) { uint4 v; asm volatile("ld.global.nc.L1::no_allocate.v4.u32 {%0,%1,%2,%3}, [%4];" : "=r"(v.x), "=r"(v.y), "=r"(v.z), "=r"(v.w) : "l"(p)); return v; }
__device__ __forceinline__ uint32_t ldg_nc(const void* p) { uint32_t v; asm volatile("ld.global.nc.u32 %0, [%1];" : "=r"(v) : "l"(p)); return v; }
__device__ __forceinline__ uint32_t ld_acquire(const uint32_t* p) { uint32_t v; asm volatile("ld.acquire.gpu.global.u32 %0, [%1];" : "=r"(v) : "l"(p) : "memory"); return v; }
__device__ __forceinline__ uint4 lds4(uint32_t a) { uint4 v; asm volatile("ld.shared.v4.u32 {%0,%1,%2,%3}, [%4];" : "=r"(v.x), "=r"(v.y), "=r"(v.z), "=r"(v.w) : "r"(a) : "memory"); return v; }
__device__ __forceinline__ float2 lds2f(uint32_t a) { float2 v; asm volatile("ld.shared.v2.f32 {%0,%1}, [%2];" : "=f"(v.x), "=f"(v.y) : "r"(a) : "memory"); return v; }
__device__ __forceinline__ uint32_t lds1(uint32_t a) { uint32_t v; asm volatile("ld.shared.u32 %0, [%1];" : "=r"(v) : "r"(a) : "memory"); return v; }
__device__ __forceinline__ void sts4(uint32_t a, uint4 v) { asm volatile("st.shared.v4.u32 [%0], {%1,%2,%3,%4};" ::"r"(a), "r"(v.x), "r"(v.y), "r"(v.z), "r"(v.w) : "memory"); }
__device__ __forceinline__ void sts2(uint32_t a, uint32_t x, uint32_t y) { asm volatile("st.shared.v2.u32 [%0], {%1,%2};" ::"r"(a), "r"(x), "r"(y) : "memory"); }
__device__ __forceinline__ void sts1(uint32_t a, uint32_t v) { asm volatile("st.shared.u32 [%0], %1;" ::"r"(a), "r"(v) : "memory"); }
__device__ __forceinline__ void stsm4(uint32_t a, uint32_t r0, uint32_t r1, uint32_t r2, uint32_t r3) {
    asm volatile("stmatrix.sync.aligned.m8n8.x4.shared.b16 [%0], {%1,%2,%3,%4};" ::"r"(a), "r"(r0), "r"(r1), "r"(r2), "r"(r3));
}
__device__ __forceinline__ uint32_t pack2(float lo, float hi) { uint32_t r; asm("cvt.rn.bf16x2.f32 %0, %1, %2;" : "=r"(r) : "f"(hi), "f"(lo)); return r; }
__device__ __forceinline__ uint32_t pack2_relu(float lo, float hi) { uint32_t r; asm("cvt.rn.relu.bf16x2.f32 %0, %1, %2;" : "=r"(r) : "f"(hi), "f"(lo)); return r; }
__device__ __forceinline__ uint32_t hfma2(uint32_t a, uint32_t b, uint32_t c) { uint32_t r; asm("fma.rn.bf16x2 %0, %1, %2, %3;" : "=r"(r) : "r"(a), "r"(b), "r"(c)); return r; }
__device__ __forceinline__ uint32_t hmul2(uint32_t a, uint32_t b) { uint32_t r; asm("mul.rn.bf16x2 %0, %1, %2;" : "=r"(r) : "r"(a), "r"(b)); return r; }
__device__ __forceinline__ float bf_lo(uint32_t v) { return __uint_as_float(v << 16); }
__device__ __forceinline__ float bf_hi(uint32_t v) { return __uint_as_float(v & 0xFFFF0000u); }
__device__ __forceinline__ float bf_round(float v) { return bf_lo(pack2(v, 0.f)); }
__device__ __forceinline__ float ex2(float x) { float r; asm("ex2.approx.ftz.f32 %0, %1;" : "=f"(r) : "f"(x)); return r; }
__device__ __forceinline__ void mma16816(float* d, uint32_t a0, uint32_t a1, uint32_t a2, uint32_t a3, uint32_t b0, uint32_t b1) {
    asm("mma.sync.aligned.m16n8k16.row.col.f32.bf16.bf16.f32 {%0,%1,%2,%3}, {%4,%5,%6,%7}, {%8,%9}, {%0,%1,%2,%3};"
        : "+f"(d[0]), "+f"(d[1]), "+f"(d[2]), "+f"(d[3]) : "r"(a0), "r"(a1), "r"(a2), "r"(a3), "r"(b0), "r"(b1));
}
__device__ __forceinline__ void mma16816_first(float* d, uint32_t a0, uint32_t a1, uint32_t a2, uint32_t a3, uint32_t b0, uint32_t b1) {
    asm volatile("mma.sync.aligned.m16n8k16.row.col.f32.bf16.bf16.f32 {%0,%1,%2,%3}, {%4,%5,%6,%7}, {%8,%9}, {%10,%10,%10,%10};"
        : "=f"(d[0]), "=f"(d[1]), "=f"(d[2]), "=f"(d[3]) : "r"(a0), "r"(a1), "r"(a2), "r"(a3), "r"(b0), "r"(b1), "f"(0.f));
}
__device__ __forceinline__ void mma16816_v(float* d, uint32_t a0, uint32_t a1, uint32_t a2, uint32_t a3, uint32_t b0, uint32_t b1) {
    asm volatile("mma.sync.aligned.m16n8k16.row.col.f32.bf16.bf16.f32 {%0,%1,%2,%3}, {%4,%5,%6,%7}, {%8,%9}, {%0,%1,%2,%3};"
        : "+f"(d[0]), "+f"(d[1]), "+f"(d[2]), "+f"(d[3]) : "r"(a0), "r"(a1), "r"(a2), "r"(a3), "r"(b0), "r"(b1));
}
__device__ __forceinline__ void mma1688(float* d, uint32_t a0, uint32_t a1, uint32_t b0) {
    asm("mma.sync.aligned.m16n8k8.row.col.f32.bf16.bf16.f32 {%0,%1,%2,%3}, {%4,%5}, {%6}, {%0,%1,%2,%3};"
        : "+f"(d[0]), "+f"(d[1]), "+f"(d[2]), "+f"(d[3]) : "r"(a0), "r"(a1), "r"(b0));
}
__device__ __forceinline__ void ldsm4(uint32_t a, uint32_t* r) {
    asm volatile("ldmatrix.sync.aligned.m8n8.x4.shared.b16 {%0,%1,%2,%3}, [%4];" : "=r"(r[0]), "=r"(r[1]), "=r"(r[2]), "=r"(r[3]) : "r"(a));
}
__device__ __forceinline__ void ldsm4t(uint32_t a, uint32_t* r) {
    asm volatile("ldmatrix.sync.aligned.m8n8.x4.trans.shared.b16 {%0,%1,%2,%3}, [%4];" : "=r"(r[0]), "=r"(r[1]), "=r"(r[2]), "=r"(r[3]) : "r"(a));
}
__device__ __forceinline__ uint32_t nz(uint32_t v) { uint32_t r; asm("max.u32 %0, %1, 1;" : "=r"(r) : "r"(v)); return r; }
__device__ __forceinline__ float rcp(float x) { float r; asm("rcp.approx.ftz.f32 %0, %1;" : "=f"(r) : "f"(x)); return r; }
__device__ __forceinline__ uint2 ld_relaxed2(const void* p) { uint2 v; asm volatile("ld.relaxed.gpu.global.v2.u32 {%0,%1}, [%2];" : "=r"(v.x), "=r"(v.y) : "l"(p) : "memory"); return v; }
__device__ __forceinline__ void st_relaxed2(void* p, uint32_t x, uint32_t y) { asm volatile("st.relaxed.gpu.global.v2.u32 [%0], {%1,%2};" ::"l"(p), "r"(max(x, 1u)), "r"(max(y, 1u)) : "memory"); }
__host__ __device__ constexpr uint64_t dconst(uint32_t lbo, uint32_t sbo, uint32_t swz) {
    return ((uint64_t)(lbo >> 4) << 16) | ((uint64_t)(sbo >> 4) << 32) | ((uint64_t)swz << 62);
}
__device__ __forceinline__ uint32_t mkdesc(uint32_t addr, uint64_t c) { return (uint32_t)c | ((addr & 0x3FFFF) >> 4); }
#define WG_FENCE() asm volatile("wgmma.fence.sync.aligned;" ::: "memory")
#define WG_COMMIT() asm volatile("wgmma.commit_group.sync.aligned;" ::: "memory")
#define WG_WAIT(n) asm volatile("wgmma.wait_group.sync.aligned %0;" ::"n"(n) : "memory")
template <int N> __device__ __forceinline__ void reg_fence(float* d) {
#pragma unroll
    for (int i = 0; i < N; i++) asm volatile("" : "+f"(d[i])::"memory");
}
template <int N> __device__ __forceinline__ void reg_def(float* d) {
#pragma unroll
    for (int i = 0; i < N; i++) asm volatile("" : "=f"(d[i]));
}
template <int N> __device__ __forceinline__ void reg_def(uint32_t* d) {
#pragma unroll
    for (int i = 0; i < N; i++) asm volatile("" : "=r"(d[i]));
}
__device__ __forceinline__ bool is_unset(uint4 v) { return min(min(v.x, v.y), min(v.z, v.w)) == 0u; }
__device__ __forceinline__ uint4 nz4(uint32_t a, uint32_t b, uint32_t c, uint32_t d) { return make_uint4(max(a, 1u), max(b, 1u), max(c, 1u), max(d, 1u)); }
__device__ __forceinline__ void wait_flags(const uint32_t* p, uint32_t target, uint32_t mask) {
    int n = 0;
    while (~__ballot_sync(~0u, ld_relaxed(p) == target) & mask) { if (++n > SPIN_LIMIT) __trap(); }
    asm volatile("fence.acquire.gpu;" ::: "memory");
}
__device__ __forceinline__ float silu_bf(uint32_t cbits) {
    const float c = __uint_as_float(cbits << 16);
    return bf_round(__fdividef(c, 1.f + fminf(ex2(-1.4426950408889634f * c), 1e30f)));
}
__device__ __forceinline__ void gemv_part(uint32_t wmbuf, int wp, int lane) {
    const uint32_t wa = wmbuf + wp * 512 + (8 * (lane >> 4) + (lane & 7)) * 32 + ((lane >> 3) & 1) * 16;
    float d[4] = {};
#pragma unroll
    for (int i = 0; i < 4; i++) {
        uint32_t A[4];
        const float2 v = lds2f(wmbuf + 28672 + (wp + 8 * i) * 32 + (lane & 3) * 8);
        ldsm4t(wa + (i < 3 || wp < 4 ? i : 0) * 4096, A);
        mma16816(d, A[0], A[1], A[2], A[3], __float_as_uint(v.x), __float_as_uint(v.y));
    }
    if ((lane & 3) == 0) {
        sts1(wmbuf + 29696 + (wp * 16 + (lane >> 2)) * 4, __float_as_uint(d[0]));
        sts1(wmbuf + 29696 + (wp * 16 + 8 + (lane >> 2)) * 4, __float_as_uint(d[2]));
    }
}
__device__ __forceinline__ uint32_t mod_word(float v, int col, uint32_t target) {
    v = bf_round(v);
    if ((col >= DM && col < 2 * DM) || (col >= 4 * DM && col < 5 * DM)) v += 1.f;
    return (pack2(v, 0.f) << 16) | (target & 0xFFFFu);
}
__device__ __forceinline__ const uint4* mod_src(int i, int r, int j, bool p2) {
    i = min(i, p2 ? 251 : 223);
    return (const uint4*)g_mod + (r & 7) * (6 * DM / 4) + (i < 224 ? (p2 ? 336 : 0) + i : (i < 238 ? 14 * j + i : 14 * j + i + 322));
}
__device__ __forceinline__ void mod_store(uint32_t sb, uint4 v, const uint4* src, int i) {
    const uint32_t tag = lds1(sb + M_EPOCH) + 1;
    while (__any_sync(~0u, (((v.x ^ tag) | (v.y ^ tag) | (v.z ^ tag) | (v.w ^ tag)) & 0xFFFFu) != 0u)) v = ld_relaxed4(src);
    if (i < 224) {
        const int isc = i >= 112, c4 = i - 112 * isc;
        const uint32_t a = sb + M_ST + (c4 >> 2) * 64 + (c4 & 1) * 32 + (c4 & 2) * 4 + (isc ? 0 : 4);
        sts1(a, __byte_perm(v.x, v.y, 0x7632));
        sts1(a + 16, __byte_perm(v.z, v.w, 0x7632));
    } else if (i < 252) {
        sts4(sb + M_G + (i - 224) * 16, make_uint4(v.x & 0xFFFF0000u, v.y & 0xFFFF0000u, v.z & 0xFFFF0000u, v.w & 0xFFFF0000u));
    }
}
__device__ __forceinline__ int pass_f(int fs, int ps) { return 224 * fs + ((fs & 1) ? (ps == 0 ? 96 : ps == 1 ? 32 : 0) : (ps == 0 ? 0 : ps == 1 ? 128 : 192)); }
__device__ __forceinline__ constexpr uint32_t slot_off(int l) { return l * 16384; }
__device__ __forceinline__ constexpr int g1_slot(int s) { return s % 7; }
__device__ __noinline__ void x1_fix(const uint32_t* g, uint32_t sa, int s) {
#pragma unroll 1
    for (int k = 4 * s; k < 4 * s + 4;) {
        const uint4 v = ld_relaxed4((const uint4*)(g + k * 256));
        sts4(sa + k * 1024, v);
        k += 2 * __all_sync(~0u, min(min(v.x, v.y), min(v.z, v.w)) != 0u);
    }
    __syncwarp();
}
struct LnRow { uint32_t nm, hi, lo; };
__device__ __forceinline__ LnRow ln_coeffs(float mean, float msq) {
    const float var = bf_round(fmaxf(msq - mean * mean, 0.f));
    float sd;
    asm("sqrt.approx.f32 %0, %1;" : "=f"(sd) : "f"(bf_round(var + 1e-5f)));
    const float inv = rcp(bf_round(sd)), hi = bf_round(inv);
    LnRow c;
    c.nm = pack2(-bf_round(mean) * hi, -bf_round(mean) * hi);
    c.hi = pack2(hi, hi);
    c.lo = pack2(inv - hi, inv - hi);
    return c;
}
__device__ __forceinline__ uint32_t hadd2(uint32_t a, uint32_t b) { uint32_t r; asm("add.rn.bf16x2 %0, %1, %2;" : "=r"(r) : "r"(a), "r"(b)); return r; }
__device__ __forceinline__ uint32_t ln_norm(uint32_t x, const LnRow& c) {
    return hfma2(x, c.hi, c.nm);
}
__device__ __forceinline__ uint32_t ln_mod(uint32_t y, uint32_t sc, uint32_t sh) {
    return hfma2(y, sc, sh);
}

#define LOADW bulk_e(dst, g_wd + (size_t)((f >> 5) * 4 + nq) * 1792, 7168, bar);
template <int sec> __device__ __forceinline__ void ring_loader(const Params& p, uint32_t sb_, int r_, int j_, int lane) {
    const uint32_t sb = opaque(sb_);
    const int r = opaque(r_), j = opaque(j_), nq = j >> 1, fs = 4 * (j & 1) + nq;
    const int fa = pass_f(fs, 0), fb = pass_f(fs, 1), fc = pass_f(fs, 2);
    const uint32_t* h2src = (const uint32_t*)__shfl_sync(~0u, (unsigned long long)(p.actb + (size_t)r * RB_WORDS + RB_H2), 0);
    const CUtensorMap* gmap = (const CUtensorMap*)__shfl_sync(~0u, (unsigned long long)(&p.ga + sec), 0);
#define BAR(i) (sb + M_BAR + 8 * (i))
#define kh (j & 1)
            int sl = 0;
#pragma unroll 1
            for (int s = 0; s < 28; s++) {
                if (s == 7) { wait_flags(g_flag + (8 * r + j) * 128 + 96 + lane, lds1(sb + M_EPOCH) + 1, 0xFFFFu); fence_async_global(); }
                const int ps = s < 14 ? 0 : s < 21 ? 1 : 2;
                const uint32_t half = ps < 2 ? 8192 : 4096;
                const int sp = sl;
                if (s >= PACE && s < PACE_END) mbar_wait(BAR(B_FULL + s - PACE), 0);
                mbar_wait(BAR(B_EMPTY + sp), (s >= 7 && s < 14) || s >= 21);
                expect_e(BAR(B_FULL + sp), half);
                tma3_e(sb + slot_off(sp) + sec * half, gmap + 2 * ps, 0, ps ? 64 * sl : 32 * s, ps == 0 ? fa >> 6 : ps == 1 ? fb >> 6 : fc >> 5, BAR(B_FULL + sp));
                sl = sl == 6 ? 0 : sl + 1;
            }
            if (!sec) PROFH(3);
#pragma unroll 1
            for (int e = 0; e < 4; e++) {
                const uint32_t dst = sb + slot_off(e) + sec * 8192, bar = BAR(B_FULL + e);
                const int f = (e < 2 ? fa + 64 * e : e == 2 ? fb : fc) + 32 * sec;
                mbar_wait(BAR(B_EMPTY + e), 0);
                expect_e(bar, e == 3 && sec ? 0 : 7168);
                if (!(e == 3 && sec)) { LOADW }
            }
            sl = 4;
            int e = 4;
#pragma unroll 1
            for (int grp = 0; grp < 9; grp++) {
                const int ps = grp >= 6 ? 2 : grp >= 3 ? 1 : 0;
                int sidx = grp - 3 * ps;
                if (sec && sidx == 0) { mbar_wait(BAR(B_HRDY + ps), 0); fence_async_global(); }
                sidx += sidx >= nq;
                int f = pass_f(4 * kh + sidx, ps);
#pragma unroll 1
                for (int k = 4 >> ps; k > 0; k--, e++, f += 32) {
                    const uint32_t dst = sb + slot_off(sl), bar = BAR(B_FULL + sl);
                    mbar_wait(BAR(B_EMPTY + sl), e >= 12 && e < 24);
                    if (e < WIN_END && e >= WIN) mbar_wait(BAR(B_FULL + (sl >= WIN ? sl - WIN : sl + 12 - WIN)), e - WIN >= 12);
                    expect_e(bar, sec ? 8192 : 7168);
                    if (!sec) { LOADW }
                    else bulk_e(dst + 8192, h2src + f * 64, 8192, bar);
                    sl = sl == 11 ? 0 : sl + 1;
                }
            }
            if (!sec) PROFH(4);
}

#define PROF_PARAMS
#define PROF_ARGS
__device__ __noinline__ void helper_late(const Params& p, int r_, int j_, int warp_ PROF_PARAMS) {
    extern __shared__ __align__(1024) unsigned char smem[];
    const uint32_t sb = (uint32_t)__cvta_generic_to_shared(smem);
    const int r = opaque(r_), j = opaque(j_), warp = opaque(warp_), nq = j >> 1, b = 8 * r + j;
    uint32_t* const act = (uint32_t*)__shfl_sync(~0u, (unsigned long long)(p.actb + (size_t)r * RB_WORDS), 0);
    {
        const int lane = fresh_tid() & 31;
        const uint32_t target = lds1(sb + M_EPOCH) + 1;
        if (warp == 8) { expect_e(BAR(B_XCH), 14336); expect_e(BAR(B_XCH + 1), 14336); }
            if (warp == 9) {
#pragma unroll 1
                for (int kv = 0; kv < 2; kv++) {
                    mbar_wait(BAR(B_PUB + kv), 0);
                    wait_flags(g_flag + b * 128 + lane, target, (r >= 2 ? 6u : r == 1 ? 2u : 0u) << (8 * kv));
                    fence_async_global();
                    const uint32_t dst = sb + OFF_Y + (kv ? Y_VR : Y_K);
                    expect_e(BAR(B_KRFULL + kv), r >= 2 ? 28672 : r == 1 ? 14336 : 0);
                    if (r >= 2) bulk_e(dst, act - 2 * RB_WORDS + RB_KV + j * 7168 + kv * 3584, 14336, BAR(B_KRFULL + kv));
                    if (r >= 1) bulk_e(dst + 14336, act - RB_WORDS + RB_KV + j * 7168 + kv * 3584, 14336, BAR(B_KRFULL + kv));
                    if (kv == 0) { PROFH(8); }
                }
            } else if (warp == 8) {
                uint4 v[8];
                mbar_wait(BAR(B_WOFULL), 0);
#pragma unroll
                for (int k = 0; k < 8; k++) v[k] = ld_relaxed4(mod_src(lane + 32 * k, r, j, true));
#pragma unroll
                for (int k = 0; k < 8; k++) mod_store(sb, v[k], mod_src(lane + 32 * k, r, j, true), lane + 32 * k);
                warp_arrive(BAR(B_MOD1));
            } else if (warp == 11) {
                if (kh == 1 && r < 14) {
                    const uint32_t wmbuf = sb + OFF_X + HALF;
                    const int mcol = 2 * DM + 32 * (4 * r + nq);
                    mbar_wait(BAR(B_XFREE), 0);
                    tma3_e(wmbuf, &p.wm2, mcol, 0, 0, BAR(B_WMFULL));
                    tma3_e(wmbuf + 14336, &p.wm2, mcol, 224, 0, BAR(B_WMFULL));
#pragma unroll 1
                    for (int wd = lane; wd < 224; wd += 32) {
                        const uint32_t cb = __ldg((const uint32_t*)p.c + wd);
                        sts1(wmbuf + 28672 + (wd >> 3) * 32 + (wd & 3) * 8 + (wd & 4), pack2(silu_bf(cb & 0xFFFFu), silu_bf(cb >> 16)));
                    }
                    __syncwarp();
                    mbar_wait(BAR(B_WMFULL), 0);
                    const uint32_t wa = wmbuf + (8 * (lane >> 4) + (lane & 7)) * 64 + ((lane >> 3) & 1) * 16;
                    float d[2][4] = {};
#pragma unroll 4
                    for (int ks = 0; ks < 28; ks++) {
                        uint32_t A[8];
                        ldsm4t(wa + ks * 1024, A); ldsm4t(wa + ks * 1024 + 32, A + 4);
                        const float2 v = lds2f(wmbuf + 28672 + ks * 32 + (lane & 3) * 8);
                        mma16816(d[0], A[0], A[1], A[2], A[3], __float_as_uint(v.x), __float_as_uint(v.y));
                        mma16816(d[1], A[4], A[5], A[6], A[7], __float_as_uint(v.x), __float_as_uint(v.y));
                    }
                    const int q = lane & 3, col = mcol + 8 * q + (lane >> 2);
                    const uint32_t word = mod_word(q == 0 ? d[0][0] : q == 1 ? d[0][2] : q == 2 ? d[1][0] : d[1][2], col, target);
#pragma unroll
                    for (int i = 0; i < 8; i++) st_relaxed(g_mod + i * 6 * DM + col, word);
                }
                warp_arrive(BAR(B_WMFREE));
                mbar_wait(BAR(B_VRFULL), 0);
                l2_prefetch_e((const char*)p.wg + (size_t)b * 12544, 12544);
                l2_prefetch_e((const char*)p.wu + (size_t)b * 12544, 12544);
#pragma unroll 1
                for (int k = 0; k < (r < 12 ? 2 : 1); k++) {
                    const int u = 28 * kh + r + 16 * k;
                    expect_e(BAR(B_XFULL + k), 7168);
                    tma3_e(sb + OFF_Y + 102400, &p.dn, 0, 32 * u, 7 * j, BAR(B_XFULL + k));
                    tma3_e(sb + OFF_Y + 102400 + 3584, &p.dn, 0, 32 * u, 7 * (j ^ 1), BAR(B_XFULL + k));
                    mbar_wait(BAR(B_XFULL + k), 1);
                    asm volatile("{\n.reg .pred p;\nelect.sync _|p, 0xffffffff;\n@p cp.async.bulk.global.shared::cta.bulk_group [%0], [%1], 7168;\n"
                                 "cp.async.bulk.commit_group;\ncp.async.bulk.wait_group 0;\n}" ::"l"(g_wd + (size_t)(u * 4 + nq) * 1792), "r"(sb + OFF_Y + 102400) : "memory");
                    __syncwarp();
                }
                warp_arrive(BAR(B_FULLK));
                fence_gpu();
                if (lane < 16) st_relaxed(g_flag + (8 * lane + j) * 128 + 96 + r, target);
            }
        if (warp == 8 || warp == 11) {
            const int sec = warp == 11;
            if (sec) ring_loader<1>(p, sb, r, j, lane); else ring_loader<0>(p, sb, r, j, lane);
            mbar_wait(BAR(B_DONE), 0);
        } else if (warp == 9) {
#pragma unroll
            for (int ev = 0; ev < 4; ev++) { expect_e(BAR(B_GFULL + ev), ev < 2 ? HALF / 2 : 16384); expect_e(BAR(B_XFULL + 2 + ev), ev < 2 ? HALF / 2 : HALF - 16384); }
            mbar_wait(BAR(B_PUB + 2), 0);
            expect_e(BAR(B_FULLV), 4096); expect_e(BAR(B_FULLQ), 4096);
            const uint32_t* fp = g_flag + b * 128 + 32 + lane;
            const int par = (target - 1) & 1;
#pragma unroll 1
            for (int n = 0, ev = 0; ev < 4; n++) {
                if (ev == 1) mbar_wait(BAR(B_PUB + 3), 0);
                uint32_t ok = __ballot_sync(~0u, ld_relaxed(fp) == target) >> (8 * ev);
                while ((ok & 0xFFu) == 0xFFu) {
                    if (ev == 1) mbar_wait(BAR(B_FULLK), 1);
                    asm volatile("fence.acquire.gpu;" ::: "memory");
                    fence_async_global();
                    const int tile = (ev & 1) + (ev >> 1) * par * 2;
                    const uint32_t dst = sb + (ev == 0 ? OFF_X : OFF_Y + (ev & 1) * HALF), first = ev < 2 ? HALF / 2 : 16384;
                    const char* src = (const char*)(act + RB_O + ((ev >> 1) * 2 + tile) * 14336);
                    if (ev >= 2) bulk_e(sb + OFF_X + X_STAT + (ev & 1) * 49152, act + RB_ST + tile * 1024, 4096, BAR(B_FULLV + (ev & 1)));
                    bulk_e(dst, src, first, BAR(B_GFULL + ev));
                    bulk_e(dst + first, src + first, HALF - first, BAR(B_XFULL + 2 + ev));
                    if (ev) PROFH(4 + ev);
                    ev++; ok >>= 8;
                }
                if (n > SPIN_LIMIT) __trap();
            }
            mbar_wait(BAR(B_XFULL + 5), 1);
#pragma unroll 1
            for (int hf = 0; hf < 2; hf++) {
                const int tile = (par ^ 1) * 2 + hf;
                uint4* xz = (uint4*)(act + RB_X1 + tile * 14336 + j * 1792) + lane;
#pragma unroll
                for (int i = 0; i < 14; i++) xz[i * 32] = make_uint4(0, 0, 0, 0);
                ((uint4*)(act + RB_ST + (tile * 8 + j) * 128))[lane] = make_uint4(0, 0, 0, 0);
            }
#pragma unroll 1
            for (int ps = 0; ps < 3; ps++) {
                mbar_wait(BAR(B_PUB + 6 + ps), 0);
                wait_flags(g_flag + b * 128 + 64 + lane, target, (0x55u << kh) << (8 * ps));
                warp_arrive(BAR(B_HRDY + ps));
                PROFH(9 + ps);
            }
        } else {
#pragma unroll 1
            for (int k = 0; k < 9; k++) {
                uint32_t* fp = k < 2 ? g_flag + (b + 8 * lane) * 128 + k * 8 + lane : g_flag + (8 * r + lane) * 128 + 16 + k * 8 + j;
                mbar_wait(BAR(B_PUB + k), 0);
                if (k != 4 && k != 5) fence_gpu();
                if (k < 2 ? (lane == 1 || lane == 2) : lane < 8) st_relaxed(fp, target);
                if (k >= 3 && k <= 5) PROFH(k - 3);
            }
        }
    }
}

__global__ void __cluster_dims__(2, 1, 1) __launch_bounds__(384, 1) fused_block_kernel(const __grid_constant__ Params p) {
    extern __shared__ __align__(1024) unsigned char smem[];
    const uint32_t sb = (uint32_t)__cvta_generic_to_shared(smem);
    const int tid = threadIdx.x, lane = tid & 31, warp = __shfl_sync(~0u, tid >> 5, 0);
    const int m = blockIdx.x >> 1;
    int r, nq;
    if (m < 4) { r = 15; nq = m; }
    else if (m < 36) { r = (m - 4) & 7; nq = (m - 4) >> 3; }
    else { nq = (m - 36) / 7; r = m - 28 - 7 * nq; }
    const int j = opaque(2 * nq + (blockIdx.x & 1)), b = 8 * r + j, fs = 4 * kh + nq;
#define act (p.actb + (size_t)r * RB_WORDS)
    constexpr uint32_t sc = 0;
    if (lane == 0 && warp < 9 && warp != 6 && warp != 7) {
        const int i0 = warp == 8 ? 0 : 8 + 8 * warp, cnt = warp == 0 || warp == 8 ? 1 : warp < 3 ? 2 : 8;
#pragma unroll
        for (int k = 0; k < 8; k++) if (i0 + k != B_WMFULL) mbar_init(BAR(i0 + k), cnt);
        if (warp == 8) mbar_init(BAR(B_WMFULL), 1);
        asm volatile("fence.mbarrier_init.release.cluster;" ::: "memory");
        fence_async_smem();
    }

    if (warp >= 8) {
        const int lane = fresh_tid() & 31;
        const bool early = kh == 0, gemv = r < 14;
        const int mcol = early ? 16 * (4 * r + nq) : 2 * DM + 32 * (4 * r + nq);
        const uint32_t wmbuf = sb + OFF_Y + HALF;
        if (warp == 8) {
            __syncwarp();
            expect_e(BAR(B_WMFULL), gemv ? 28672 >> early : 0);
            if (early && gemv) { tma3_e(wmbuf, &p.wm, mcol, 0, 0, BAR(B_WMFULL)); tma3_e(wmbuf + 7168, &p.wm, mcol, 224, 0, BAR(B_WMFULL)); }
#pragma unroll
            for (int kb = 0; kb < XFIRST; kb++) {
                expect_e(BAR(B_XFULL + kb), 16384);
                tma3_e(sb + OFF_X + kb * 16384, &p.xm, 64 * kb, 128 * r, 0, BAR(B_XFULL + kb));
            }
        }
        asm volatile("setmaxnreg.dec.sync.aligned.u32 56;");
        if (warp == 9) {
#pragma unroll
            for (int i = 56; i < 64; i++) init_e(BAR(i), 1);
            fence_async_smem();
        }
        bar_arrive(0, 384);
        asm volatile("barrier.cluster.arrive.relaxed.aligned;" ::: "memory");
        if (warp == 8) {
#pragma unroll
            for (int kb = XFIRST; kb < 7; kb++) {
                expect_e(BAR(B_XFULL + kb), 16384);
                tma3_e(sb + OFF_X + kb * 16384, &p.xm, 64 * kb, 128 * r, 0, BAR(B_XFULL + kb));
            }
            if (KDELAY >= 0) { mbar_wait(BAR(B_XFULL + KDELAY), 0); l2_prefetch_e((const char*)p.wqkv + (size_t)b * 9408, 9408); }
#pragma unroll 1
            for (int mt = 0; mt < 4; mt++) {
                if (mt == 1) bar_sync(9, 384);
                if (mt == 3) mbar_wait(BAR(B_WMFREE), 0);
                if (mt == 1 && early) mbar_wait(BAR(B_WMFREE), 0);
                if (mt) mbar_wait(BAR(mt == 1 ? (VGATE == 1 ? B_XFREE : B_FULLK) : mt == 2 ? B_MOD1 : B_VRFULL), 0);
                const uint32_t bar = BAR(mt == 3 ? B_WOFULL : B_FULLK + mt), dst = sb + (mt < 2 ? OFF_Y : OFF_X) + (mt & 1) * HALF;
                const int c0 = (mt < 2 ? DM + DM * mt : 0) + 56 * j - 8 * kh;
                if (!sc) {
                    expect_e(bar, HALF);
                    tma3_e(dst, mt == 3 ? &p.wo : &p.qkv, c0, 0, 0, bar);
                    tma3_e(dst + HALF / 2, mt == 3 ? &p.wo : &p.qkv, c0, 224, 0, bar);
                }
            }
        } else {
            if (KDELAY < 0 && warp == 10) l2_prefetch_e((const char*)p.wqkv + (size_t)b * 9408, 9408);
            bar_sync(9, 384);
            if (sc) return;
            if (warp == 11 && early) {
                const uint32_t target = lds1(sb + M_EPOCH) + 1;
                mbar_wait(BAR(B_GEMV), 0);
                float sum = 0.f;
#pragma unroll
                for (int i = 0; i < 8; i++) sum += *(const float*)(smem + OFF_Y + HALF + 29696 + (i * 16 + (lane & 15)) * 4);
                uint32_t* mg = g_mod + mcol + (lane & 15) + (lane >> 4) * 4 * 6 * DM;
                const uint32_t word = mod_word(sum, mcol, target);
                if (gemv) { st_relaxed(mg, word); st_relaxed(mg + 6 * DM, word); st_relaxed(mg + 12 * DM, word); st_relaxed(mg + 18 * DM, word); }
            }
        }
    }
    if (LIKELY(warp < 8)) {
        const int w = (warp >> 2) ^ WSWAP, wi = warp & 3;
#define COORDS const int t = fresh_tid() & 127, lane = t & 31, q = lane & 3, lr = lane >> 2, ra = 64 * w + 16 * wi + lr; \
        const uint32_t lx = (lane >> 4) ^ (lane & 7), mrow = (64 * w + 16 * wi + ((lane >> 3) & 1) * 8 + (lane & 7)) * 128; \
        (void)q; (void)lr; (void)ra; (void)lx; (void)mrow;
        const int sid = 2 * (j & 3) + w;
#define RUN(k) (!sc || sid == (k))
#define WAIT(i, par) mbar_wait_c(BAR(i), (par) | sc)
        constexpr uint64_t DB128 = dconst(4096, 1024, 1);
        {
            const int wd = fresh_tid();
            const uint32_t cb = wd < 224 ? __ldg((const uint32_t*)p.c + wd) : 0u;
            if (wd == 255 && !sc) sts1(sb + M_EPOCH, atomicAdd(&g_ticket, 1u) / NCTA);
            sts1(sb + OFF_Y + HALF + 28672 + (wd >> 3) * 32 + (wd & 3) * 8 + (wd & 4), pack2(silu_bf(cb & 0xFFFFu), silu_bf(cb >> 16)));
        }
        bar_arrive(9, 384);
        bar_sync(0, 384);
        asm volatile("barrier.cluster.arrive.relaxed.aligned;" ::: "memory");
        asm volatile("setmaxnreg.inc.sync.aligned.u32 224;");
        PROFC(0);
        uint32_t xr[16];
        {
            COORDS
            uint32_t h[112];
            LnRow ca, cb;
            const int mi = min(128 * w + t, 223);
            const uint4* msrc = mod_src(mi, r, j, false);
            uint4 mv;
            {
                float ds[4] = {}, da[2][4] = {}, db[2][4] = {};
                const uint32_t ONE2 = 0x3F803F80u;
#pragma unroll
                for (int kb = 0; kb < 7; kb++) {
                    if (kb == GEMV_AT && kh == 0) { WAIT(B_WMFULL, 0); gemv_part(sb + OFF_Y + HALF, warp, lane); warp_arrive(BAR(B_GEMV)); }
                    WAIT(B_XFULL + kb, 0);
#pragma unroll
                    for (int k4 = 0; k4 < 4; k4++) ldsm4(sb + OFF_X + mrow + kb * 16384 + (((2 * k4) ^ lx) << 4), h + 16 * kb + 4 * k4);
#pragma unroll
                    for (int k4 = 0; k4 < 4; k4++) {
                        const uint32_t* f = h + 16 * kb + 4 * k4;
                        mma16816(ds, f[0], f[1], f[2], f[3], ONE2, ONE2);
                        mma1688(da[0], f[0], f[1], f[0]); mma1688(db[0], f[0], f[1], f[1]);
                        mma1688(da[1], f[2], f[3], f[2]); mma1688(db[1], f[2], f[3], f[3]);
                    }
                }
#pragma unroll
                for (int i = 0; i < 4; i++) {
                    const int ch = 7 * j + 2 * i + (lane >> 4);
                    ldsm4(sb + OFF_X + mrow + (ch >> 3) * 16384 + (((ch ^ lane) & 7) << 4), xr + 4 * i);
                }
                mv = ld_relaxed4(msrc);
                warp_arrive(BAR(B_XFREE));
                float qa = (lr & 1) ? da[0][1] + da[1][1] : da[0][0] + da[1][0];
                float qb = (lr & 1) ? db[0][3] + db[1][3] : db[0][2] + db[1][2];
                const int src = (lane & ~3) | (lr >> 1);
                qa = __shfl_sync(~0u, qa, src);
                qb = __shfl_sync(~0u, qb, src);
                ca = ln_coeffs(ds[0] * (1.f / DM), qa * (1.f / DM));
                cb = ln_coeffs(ds[2] * (1.f / DM), qb * (1.f / DM));
#pragma unroll
                for (int i = 0; i < 4 * NPRE; i += 2) { h[i] = ln_norm(h[i], ca); h[i + 1] = ln_norm(h[i + 1], cb); }
            }
            PROFC(1);
            {
                float ak[28], av[28], aq[28];
                uint32_t kp[14], vp[14];
                const uint64_t bq0 = (DB128 & ~0xFFFFFFFFull) | (mkdesc(sb + OFF_X, DB128) + kh), bk0 = bq0 + (OFF_Y >> 4), bv0 = bk0 + (HALF >> 4);
                uint32_t* kvg = act + RB_KV + j * 7168 + (8 * w + 2 * wi) * 224 + lane;
                mod_store(sb, mv, msrc, mi);
                bar_sync(3, 256);
                if (warp == 0) warp_arrive(BAR(B_MOD1));
                WAIT(B_FULLK, 0);
                PROFC(2);
                reg_def<28>(ak);
#pragma unroll
                for (int g4 = 0; g4 < 4; g4++) {
#pragma unroll
                    for (int ks = 7 * g4; ks < 7 * g4 + 7; ks++) {
                        const uint4 st = *(const uint4*)(smem + M_ST + ks * 64 + q * 16);
                        if (ks >= NPRE) {
                            h[4 * ks] = ln_norm(h[4 * ks], ca); h[4 * ks + 1] = ln_norm(h[4 * ks + 1], cb);
                            h[4 * ks + 2] = ln_norm(h[4 * ks + 2], ca); h[4 * ks + 3] = ln_norm(h[4 * ks + 3], cb);
                        }
                        h[4 * ks] = ln_mod(h[4 * ks], st.x, st.y); h[4 * ks + 1] = ln_mod(h[4 * ks + 1], st.x, st.y);
                        h[4 * ks + 2] = ln_mod(h[4 * ks + 2], st.z, st.w); h[4 * ks + 3] = ln_mod(h[4 * ks + 3], st.z, st.w);
                    }
                    WG_FENCE();
#pragma unroll
                    for (int ks = 7 * g4; ks < 7 * g4 + 7; ks++) wgmma_rl_56(ak, h[4 * ks], h[4 * ks + 1], h[4 * ks + 2], h[4 * ks + 3], bk0 + ks * 128, ks != 0);
                }
                WG_COMMIT();
                PROFC(3);
                reg_def<28>(av);
                WG_WAIT(0);
                reg_fence<28>(ak);
#pragma unroll
                for (int g = 0; g < 7; g++) {
                    kp[2 * g] = pack2(ak[4 * g], ak[4 * g + 1]); kp[2 * g + 1] = pack2(ak[4 * g + 2], ak[4 * g + 3]);
                    kvg[g * 32] = kp[2 * g]; kvg[224 + g * 32] = kp[2 * g + 1];
                }
                warp_arrive(BAR(B_PUB));
                PROFC(4);
                if (KEARLY) WAIT(B_FULLV, 0);
                WG_FENCE();
#pragma unroll
                for (int ks = KEARLY ? 0 : 8; ks < 28; ks++) wgmma_rl_56(av, h[4 * ks], h[4 * ks + 1], h[4 * ks + 2], h[4 * ks + 3], bv0 + ks * 128, ks != 0);
                WG_COMMIT();
                reg_def<28>(aq);
                WAIT(B_FULLQ, 0);
                WG_FENCE();
#pragma unroll
                for (int ks = 0; ks < VPRE; ks++) wgmma_rl_56(aq, h[4 * ks], h[4 * ks + 1], h[4 * ks + 2], h[4 * ks + 3], bq0 + ks * 128, ks != 0);
                WG_COMMIT();
                WG_WAIT(1);
                reg_fence<28>(av);
#pragma unroll
                for (int g = 0; g < 7; g++) {
                    vp[2 * g] = pack2(av[4 * g], av[4 * g + 1]); vp[2 * g + 1] = pack2(av[4 * g + 2], av[4 * g + 3]);
                    kvg[3584 + g * 32] = vp[2 * g]; kvg[3584 + 224 + g * 32] = vp[2 * g + 1];
                }
                warp_arrive(BAR(B_PUB + 1));
                PROFC(5);
                if (!VPRE) WAIT(B_FULLQ, 0);
                WG_FENCE();
#pragma unroll
                for (int ks = VPRE; ks < 28; ks++) wgmma_rl_56(aq, h[4 * ks], h[4 * ks + 1], h[4 * ks + 2], h[4 * ks + 3], bq0 + ks * 128, ks != 0);
                WG_COMMIT();
                WAIT(B_PUB + 1, 0);
                const uint32_t rg = 8 * w + 2 * wi + ((lane >> 3) & 1);
                const uint32_t ko = sb + OFF_Y + Y_KOWN + rg * 896 + (lane & 7) * 16, qo = sb + OFF_Y + Y_Q + rg * 1024 + (lane >> 4) * 128 + (lane & 7) * 16;
#pragma unroll
                for (int g = 0; g < 6; g += 2) {
                    stsm4(ko + (g + (lane >> 4)) * 128, kp[2 * g], kp[2 * g + 1], kp[2 * g + 2], kp[2 * g + 3]);
                    stsm4(ko + (Y_VOWN - Y_KOWN) + (g + (lane >> 4)) * 128, vp[2 * g], vp[2 * g + 1], vp[2 * g + 2], vp[2 * g + 3]);
                }
                stsm4(ko + (lane >> 4) * (Y_VOWN - Y_KOWN) + 6 * 128, kp[12], kp[13], vp[12], vp[13]);
                WG_WAIT(0);
                reg_fence<28>(aq);
                __syncwarp();
                if (lane < 3 && w == 1) mbar_arrive(BAR(B_EMPTY + lane));
                uint32_t qp[14];
#pragma unroll
                for (int i = 0; i < 14; i++) qp[i] = pack2(aq[2 * i], aq[2 * i + 1]);
                stsm4(qo, qp[0], qp[1], qp[2], qp[3]);
                stsm4(qo + 256, qp[4], qp[5], q < 2 ? qp[6] : 0u, q < 2 ? qp[7] : 0u);
                stsm4(qo + 512, q < 2 ? 0u : qp[6], q < 2 ? 0u : qp[7], qp[8], qp[9]);
                stsm4(qo + 768, qp[10], qp[11], qp[12], qp[13]);
                fence_async_smem();
                if (w == 0) { bar_arrive(4, 256); bar_sync(1, 128); } else { bar_arrive(5, 256); bar_sync(4, 256); }
            }
        }
        PROFC(6);
        WAIT(B_KRFULL, 0);
        if (ATT_OFF && w == ATT_WG) { const uint32_t t0 = clock(); while (clock() - t0 < ATT_OFF) {} }
        PROFC(7);
        if (RUN(2)) {
#pragma unroll 1
            for (int hf = sc; hf < 2; hf++) {
                COORDS
                if (ASYM && hf > w) bar_sync(5, 256);
                float s[160];
                const float CS = 0.18898223650461361f * 1.4426950408889634f;
                const float NEG = __int_as_float(0xFF800000);
                constexpr uint64_t DQ = dconst(128, 1024, 0), DK = dconst(128, 896, 0);
                {
                    const uint32_t qd = mkdesc(sb + OFF_Y + Y_Q + hf * 8192 + w * 512, DQ), kd = mkdesc(sb + OFF_Y + Y_K + hf * 8 * 896 + w * 384, DK);
                    reg_def<160>(s);
                    WG_FENCE();
                    wgmma_sk_160<DQ, DK>(s, qd, kd, 0);
                    wgmma_sk_160<DQ, DK>(s, qd + 16, kd + 16, 1);
                    wgmma_sk_160<DQ, DK>(s + 80, qd, kd + 20 * 56, 0);
                    wgmma_sk_160<DQ, DK>(s + 80, qd + 16, kd + 20 * 56 + 16, 1);
                    WG_COMMIT();
                    WG_WAIT(0);
                    reg_fence<160>(s);
                }
                if (r < 2) {
                    const int pmin = 4 - 2 * r - hf;
#pragma unroll
                    for (int p4 = 0; p4 < 4; p4++)
                        if (p4 < pmin) {
#pragma unroll
                            for (int i = 0; i < 32; i++) asm volatile("mov.b32 %0, 0xFF800000;" : "=f"(s[32 * p4 + i]));
                        }
                }
                const bool c0 = 2 * q > lr, c1 = 2 * q + 1 > lr;
#pragma unroll
                for (int pp = 0; pp < 4; pp++) {
                    const bool me = pp == wi;
                    float* e = s + 8 * pp;
                    if (me && !c0) { e[0] = NEG; e[6] = NEG; }
                    if (me && !c1) { e[1] = NEG; e[7] = NEG; }
                    if (me) { e[2] = NEG; e[3] = NEG; }
                    e = s + 8 * (pp + 16);
                    if (me && c0) { e[0] = NEG; e[6] = NEG; }
                    if (me && c1) { e[1] = NEG; e[7] = NEG; }
                    if (me) { e[4] = NEG; e[5] = NEG; }
                }
#pragma unroll
                for (int i = 0; i < 24; i++) s[i] = (i >> 3) < wi ? s[136 + i] : s[i];
                int i0 = 0x80000000, i1 = 0x80000000, i2 = 0x80000000, i3 = 0x80000000;
#pragma unroll
                for (int pp = 0; pp < 17; pp++) {
                    const float* e = s + 8 * pp;
                    i0 = __vimax3_s32(i0, __float_as_int(e[0]), __float_as_int(e[1])); i1 = __vimax3_s32(i1, __float_as_int(e[2]), __float_as_int(e[3]));
                    i2 = __vimax3_s32(i2, __float_as_int(e[4]), __float_as_int(e[5])); i3 = __vimax3_s32(i3, __float_as_int(e[6]), __float_as_int(e[7]));
                }
                i0 = max(i0, i2); i1 = max(i1, i3);
                i0 = max(i0, __shfl_xor_sync(~0u, i0, 1)); i1 = max(i1, __shfl_xor_sync(~0u, i1, 1));
                i0 = max(i0, __shfl_xor_sync(~0u, i0, 2)); i1 = max(i1, __shfl_xor_sync(~0u, i1, 2));
                if (__any_sync(~0u, (i0 | i1) < 0)) {
                    uint32_t u0 = ~0u, u1 = ~0u, u2 = ~0u, u3 = ~0u;
#pragma unroll
                    for (int pp = 0; pp < 17; pp++) {
                        const float* e = s + 8 * pp;
                        u0 = __vimin3_u32(u0, __float_as_uint(e[0]), __float_as_uint(e[1])); u1 = __vimin3_u32(u1, __float_as_uint(e[2]), __float_as_uint(e[3]));
                        u2 = __vimin3_u32(u2, __float_as_uint(e[4]), __float_as_uint(e[5])); u3 = __vimin3_u32(u3, __float_as_uint(e[6]), __float_as_uint(e[7]));
                    }
                    u0 = min(u0, u2); u1 = min(u1, u3);
                    u0 = min(u0, __shfl_xor_sync(~0u, u0, 1)); u1 = min(u1, __shfl_xor_sync(~0u, u1, 1));
                    u0 = min(u0, __shfl_xor_sync(~0u, u0, 2)); u1 = min(u1, __shfl_xor_sync(~0u, u1, 2));
                    if (i0 < 0) i0 = u0;
                    if (i1 < 0) i1 = u1;
                }
                const float ma = __int_as_float(i0), mb = __int_as_float(i1);
                const float na = -ma * CS, nb = -mb * CS;
                PROFC(8 + 3 * hf);
                {
                    WAIT(B_VRFULL, 0);
                    float o[16] = {}, rs[4] = {};
                    const uint32_t va = sb + OFF_Y + Y_VR + (8 * hf + ((lane >> 3) & 1)) * 896 + (3 * w + (lane >> 4)) * 128 + (lane & 7) * 16;
                    constexpr uint32_t OWN = Y_VOWN - 32 * 896;
#pragma unroll
                    for (int pp = 0; pp < 17; pp++) {
                        uint32_t B[8];
                        const uint32_t v = va + pp * 1792 + (pp < 3 ? (pp < wi ? 17 * 1792 + OWN : 0) : pp == 16 ? OWN : pp >= 12 ? hf * OWN : 0);
                        ldsm4t(v, B); ldsm4t(v + 256, B + 4);
                        float e[8];
#pragma unroll
                        for (int i = 0; i < 8; i++) e[i] = ex2(fmaf(s[8 * pp + i], CS, (i & 2) ? nb : na));
                        const uint32_t p0 = pack2(e[0], e[1]), p1 = pack2(e[2], e[3]), p2 = pack2(e[4], e[5]), p3 = pack2(e[6], e[7]);
                        mma16816(rs, p0, p1, p2, p3, 0x3F803F80u, 0x3F803F80u);
#pragma unroll
                        for (int g = 0; g < 4; g++) mma16816(o + 4 * g, p0, p1, p2, p3, B[2 * g], B[2 * g + 1]);
                    }
                    PROFC(9 + 3 * hf);
                    const float ia = rcp(rs[0]), ib = rcp(rs[2]);
                    uint32_t* og = act + RB_O + hf * 14336 + (7 * j + 3 * w) * 256 + wi * 64 + lane;
#pragma unroll
                    for (int g = 0; g < 4; g++) {
                        if ((g == 3 - 3 * w) ? ((q >> 1) == w) : true) {
                            og[g * 256] = pack2(o[4 * g] * ia, o[4 * g + 1] * ia);
                            og[g * 256 + 32] = pack2(o[4 * g + 2] * ib, o[4 * g + 3] * ib);
                        }
                    }
                    warp_arrive(BAR(B_PUB + 2 + hf));
                    PROFC(10 + 3 * hf);
                }
            }
        }
        uint32_t x1p[14];
        COORDS
        constexpr uint64_t DT = dconst(1024, 128, 0);
        const int tile = opaque((lds1(sb + M_EPOCH) & 1) * 2 + w);
        if (RUN(4)) {
            float ac[28];
            const uint32_t ad = mkdesc(sb + (w ? OFF_Y + HALF : OFF_X), DT), bd = mkdesc(sb + OFF_X + HALF, DB128) + kh;
            WAIT(B_WOFULL, 0);
            WAIT(B_MOD1, 1);
            WAIT(B_GFULL + w, 0);
            PROFC(28);
            reg_def<28>(ac);
#pragma unroll 1
            for (int u = 0; u < 4; u++) {
                if (u == 2) WAIT(B_XFULL + 2 + w, 1);
                WG_FENCE();
#pragma unroll
                for (int i = 0; i < 7; i++) wgmma_ss_56<DT, DB128>(ac, ad + (7 * u + i) * 128, bd + (7 * u + i) * 128, (u | i) != 0);
            }
            WG_COMMIT();
            WG_WAIT(0);
            reg_fence<28>(ac);
            PROFC(14);
            __syncwarp();
            if (lane < 3) mbar_arrive(BAR(B_EMPTY + 4 - w + lane));
            if (lane < 3 && w == 0) mbar_arrive(BAR(B_EMPTY + lane));
            float ds[4] = {}, da[4] = {}, db[4] = {};
            uint32_t* xo = act + RB_X1 + tile * 14336 + 7 * j * 256 + wi * 64 + lane;
#pragma unroll
            for (int g = 0; g < 7; g++) {
                const float2 ga = *(const float2*)(smem + M_G + (8 * g + 2 * q) * 4);
                x1p[2 * g] = pack2(fmaf(ga.x, ac[4 * g], bf_lo(xr[2 * g])), fmaf(ga.y, ac[4 * g + 1], bf_hi(xr[2 * g])));
                x1p[2 * g + 1] = pack2(fmaf(ga.x, ac[4 * g + 2], bf_lo(xr[2 * g + 1])), fmaf(ga.y, ac[4 * g + 3], bf_hi(xr[2 * g + 1])));
                st_relaxed(xo + g * 256, nz(x1p[2 * g])); st_relaxed(xo + g * 256 + 32, nz(x1p[2 * g + 1]));
                mma1688(ds, x1p[2 * g], x1p[2 * g + 1], 0x3F803F80u);
                mma1688(da, x1p[2 * g], x1p[2 * g + 1], x1p[2 * g]);
                mma1688(db, x1p[2 * g], x1p[2 * g + 1], x1p[2 * g + 1]);
            }
            const int src = (lane & ~3) | (lr >> 1);
            const float qa = __shfl_sync(~0u, (lr & 1) ? da[1] : da[0], src), qb = __shfl_sync(~0u, (lr & 1) ? db[3] : db[2], src);
            const float kk = (q & 1) ? ((q & 2) ? qb : qa) : ((q & 2) ? ds[2] : ds[0]);
            st_relaxed(act + RB_ST + ((tile * 8 + j) * 64 + 16 * wi + lr + 4 * (q & 2)) * 2 + (q & 1), nz(__float_as_uint(kk)));
            __syncwarp();
            if (lane < 2) mbar_arrive(BAR(B_PUB + 4 + w));
        } else reg_def<14>(x1p);
        PROFC(15);
        uint32_t h2a[32], h2b[24];
        {
            const int fa = pass_f(fs, 0), fb = pass_f(fs, 1), fc = pass_f(fs, 2);
            uint32_t* h2g = act + RB_H2 + (8 * w + 2 * wi) * 32 + lane;
            const uint32_t a0 = mkdesc(sb + OFF_Y + w * HALF, DT);
            if (RUN(3)) {
                LnRow ca, cb;
                {
                    const uint32_t* sg = act + RB_ST + ((tile * 8 + 2 * q) * 64 + 16 * wi + lr) * 2;
                    uint2 u[4];
                    WAIT(B_FULLV + w, 1);
                    PROFC(16);
#pragma unroll
                    for (int i = 0; i < 4; i++) { const float2 v = lds2f(sb + OFF_X + X_STAT + w * 49152 + ((2 * q + (i >> 1)) * 64 + 16 * wi + lr + 8 * (i & 1)) * 8); u[i] = make_uint2(__float_as_uint(v.x), __float_as_uint(v.y)); }
                    while (__any_sync(~0u, min(min(min(u[0].x, u[0].y), min(u[1].x, u[1].y)), min(min(u[2].x, u[2].y), min(u[3].x, u[3].y))) < 1u - sc)) {
#pragma unroll
                        for (int i = 0; i < 4; i++) u[i] = ld_relaxed2(sg + (i >> 1) * 128 + (i & 1) * 16);
                    }
                    warp_arrive(BAR(B_EMPTY + 3 + 3 * w));
                    float v[4] = {__uint_as_float(u[0].x) + __uint_as_float(u[2].x), __uint_as_float(u[0].y) + __uint_as_float(u[2].y),
                                  __uint_as_float(u[1].x) + __uint_as_float(u[3].x), __uint_as_float(u[1].y) + __uint_as_float(u[3].y)};
#pragma unroll
                    for (int i = 0; i < 4; i++) { v[i] += __shfl_xor_sync(~0u, v[i], 1); v[i] += __shfl_xor_sync(~0u, v[i], 2); }
                    ca = ln_coeffs(v[0] * (1.f / DM), v[1] * (1.f / DM));
                    cb = ln_coeffs(v[2] * (1.f / DM), v[3] * (1.f / DM));
                }
                const uint32_t ha = sb + OFF_Y + w * HALF + (lane >> 4) * 1024 + (2 * wi + ((lane >> 3) & 1)) * 128 + (lane & 7) * 16;
                const uint32_t sta = sb + M_ST + q * 16;
                const uint32_t* xg = act + RB_X1 + tile * 14336 + (lane >> 4) * 256 + wi * 64 + (lane & 15) * 4;
                uint32_t x[8];
                const uint32_t xs = sb + OFF_Y + w * HALF + (lane >> 4) * 1024 + wi * 256 + (lane & 15) * 16;
                uint4 st[2];
                auto load = [&](int s) {
                    if (s == 4) mbar_wait_c(BAR(B_XFULL + 4 + w), 1);
                    ldsm4(ha + s * 4096, x); ldsm4(ha + s * 4096 + 2048, x + 4);
                    st[0] = lds4(sta + s * 128); st[1] = lds4(sta + s * 128 + 64);
                };
                auto prep = [&](int s, uint32_t* f) {
                    if (__any_sync(~0u, min(min(min(x[0], x[1]), min(x[2], x[3])), min(min(x[4], x[5]), min(x[6], x[7]))) < 1u - sc)) {
                        WG_WAIT(0);
                        x1_fix(xg, xs, s);
                        ldsm4(ha + s * 4096, x); ldsm4(ha + s * 4096 + 2048, x + 4);
                    }
#pragma unroll
                    for (int i = 0; i < 2; i++) {
                        f[4 * i] = ln_mod(ln_norm(x[4 * i], ca), st[i].x, st[i].y); f[4 * i + 1] = ln_mod(ln_norm(x[4 * i + 1], cb), st[i].x, st[i].y);
                        f[4 * i + 2] = ln_mod(ln_norm(x[4 * i + 2], ca), st[i].z, st[i].w); f[4 * i + 3] = ln_mod(ln_norm(x[4 * i + 3], cb), st[i].z, st[i].w);
                    }
                    if (s < 13) load(s + 1);
                    stsm4(ha + s * 4096, f[0], f[1], f[2], f[3]); stsm4(ha + s * 4096 + 2048, f[4], f[5], f[6], f[7]);
                };
                float ac[128];
                uint32_t fr[3][8];
                uint64_t bd = (DB128 & ~0xFFFFFFFFull) | mkdesc(sb, DB128);
                reg_def<128>(ac);
                WAIT(B_GFULL + 2 + w, 0);
                load(0);
                prep(0, fr[0]);
                PROFC(17);
#pragma unroll
                for (int s = 0; s < 14; s++) {
                    const uint32_t* f = fr[s % 3];
                    WAIT(B_FULL + g1_slot(s), s >= 7);
                    WG_FENCE();
                    wgmma_rl_256(ac, f[0], f[1], f[2], f[3], bd, s != 0);
                    wgmma_rl_256(ac, f[4], f[5], f[6], f[7], bd + 128, 1);
                    bd += s == 6 ? p.zero - 6 * 1024ull : 1024;
                    WG_COMMIT();
                    if (s < 13) prep(s + 1, fr[(s + 1) % 3]);
                    if (s > 0) { WG_WAIT(1); warp_arrive(BAR(B_EMPTY + g1_slot(s - 1))); }
                }
                fence_async_smem();
                PROFC(18);
                WG_WAIT(0);
                reg_fence<128>(ac);
                warp_arrive(BAR(B_EMPTY + 6));
#pragma unroll
                for (int g = 0; g < 16; g++) {
                    h2a[2 * g] = hmul2(pack2_relu(ac[4 * g], ac[4 * g + 1]), pack2(ac[64 + 4 * g], ac[64 + 4 * g + 1]));
                    h2a[2 * g + 1] = hmul2(pack2_relu(ac[4 * g + 2], ac[4 * g + 3]), pack2(ac[64 + 4 * g + 2], ac[64 + 4 * g + 3]));
                }
                bar_sync(1 + w, 128);
            } else reg_def<32>(h2a);
            PROFC(19);
            if (RUN(5)) {
                float ac[64];
                reg_def<64>(ac);
                const uint32_t bx = mkdesc(sb, dconst(8192, 1024, 1));
#pragma unroll kB
                for (int s = 0; s < 7; s++) {
                    WAIT(B_FULL + s, 0);
                    const uint32_t ad = a0 + s * 512, bd = bx + (slot_off(s) >> 4);
                    WG_FENCE();
#pragma unroll
                    for (int k = 0; k < 4; k++) wgmma_ss_128<DT, DB128>(ac, ad + k * 128, bd + k * 128, (s | k) != 0);
                    WG_COMMIT();
                    if (s == 1) {
#pragma unroll
                        for (int g = 0; g < 16; g++) { h2g[(fa / 8 + g) * 512] = h2a[2 * g]; h2g[(fa / 8 + g) * 512 + 32] = h2a[2 * g + 1]; }
                        warp_arrive(BAR(B_PUB + 6));
                    }
                    if (s > 0) { WG_WAIT(1); warp_arrive(BAR(B_EMPTY + s - 1)); }
                }
                WG_WAIT(0);
                reg_fence<64>(ac);
                warp_arrive(BAR(B_EMPTY + 6));
#pragma unroll
                for (int g = 0; g < 8; g++) {
                    h2b[2 * g] = hmul2(pack2_relu(ac[4 * g], ac[4 * g + 1]), pack2(ac[32 + 4 * g], ac[32 + 4 * g + 1]));
                    h2b[2 * g + 1] = hmul2(pack2_relu(ac[4 * g + 2], ac[4 * g + 3]), pack2(ac[32 + 4 * g + 2], ac[32 + 4 * g + 3]));
                }
            } else reg_def<16>(h2b);
            PROFC(27);
            if (RUN(6)) {
                float ac[32];
                reg_def<32>(ac);
                const uint32_t bx = mkdesc(sb, dconst(4096, 512, 2));
#pragma unroll kC
                for (int s = 0; s < 7; s++) {
                    WAIT(B_FULL + s, 1);
                    const uint32_t ad = a0 + s * 512, bd = bx + (slot_off(s) >> 4);
                    WG_FENCE();
#pragma unroll
                    for (int k = 0; k < 4; k++) wgmma_ss_64<DT, dconst(4096, 512, 2)>(ac, ad + k * 128, bd + k * 64, (s | k) != 0);
                    WG_COMMIT();
                    if (s == 1) {
#pragma unroll
                        for (int g = 0; g < 8; g++) { h2g[(fb / 8 + g) * 512] = h2b[2 * g]; h2g[(fb / 8 + g) * 512 + 32] = h2b[2 * g + 1]; }
                        warp_arrive(BAR(B_PUB + 7));
                    }
                    if (s > 0) { WG_WAIT(1); warp_arrive(BAR(B_EMPTY + s - 1)); }
                }
                WG_WAIT(0);
                reg_fence<32>(ac);
                __syncwarp();
                if (lane < 6) mbar_arrive(BAR(B_EMPTY + 6 + lane));
                PROFC(20);
#pragma unroll
                for (int g = 0; g < 4; g++) {
                    h2b[16 + 2 * g] = hmul2(pack2_relu(ac[4 * g], ac[4 * g + 1]), pack2(ac[16 + 4 * g], ac[16 + 4 * g + 1]));
                    h2b[16 + 2 * g + 1] = hmul2(pack2_relu(ac[4 * g + 2], ac[4 * g + 3]), pack2(ac[16 + 4 * g + 2], ac[16 + 4 * g + 3]));
                    h2g[(fc / 8 + g) * 512] = h2b[16 + 2 * g]; h2g[(fc / 8 + g) * 512 + 32] = h2b[16 + 2 * g + 1];
                }
                warp_arrive(BAR(B_PUB + 8));
                asm volatile("barrier.cluster.wait.aligned;" ::: "memory");
                if (lane == 0 && !sc) {
                    uint32_t rb;
                    asm volatile("mapa.shared::cluster.u32 %0, %1, %2;" : "=r"(rb) : "r"(BAR(B_PEER)), "r"(kh ^ 1));
                    asm volatile("mbarrier.arrive.relaxed.cluster.shared::cluster.b64 _, [%0];" ::"r"(rb) : "memory");
                }
            } else reg_def<8>(h2b + 16);
        }
        PROFC(21);
        if (RUN(7)) {
            float ac[56];
            reg_def<56>(ac);
            constexpr uint64_t DAN = dconst(2048, 128, 0);
            constexpr uint64_t DW = dconst(128, 512, 0);
            const uint32_t bx = mkdesc(sb, DW);
#pragma unroll
            for (int e = 0; e < 4; e++) {
                WAIT(B_FULL + e, 0);
                const uint64_t bd = ((DW & ~0xFFFFFFFFull) | bx) + (slot_off(e) >> 4);
                const uint32_t* hh = e < 2 ? h2a + 16 * e : h2b + 16 * (e - 2);
                WG_FENCE();
#pragma unroll
                for (int k = 0; k < (e < 3 ? 4 : 2); k++) wgmma_rl_112(ac, hh[4 * k], hh[4 * k + 1], hh[4 * k + 2], hh[4 * k + 3], bd + (k >> 1) * 512 + (k & 1) * 16, (e | k) != 0);
                WG_COMMIT();
                if (e > 0) { WG_WAIT(1); warp_arrive(BAR(B_EMPTY + e - 1)); }
            }
            PROFC(22);
            uint32_t ad = mkdesc(sb + 4 * 16384 + 8192 + w * 1024, DAN), bd = bx + 4 * 1024, fb_ = BAR(B_FULL + 4), eb_ = BAR(B_EMPTY + 3), par = sc;
#pragma unroll 1
            for (int e = 4; e < 25; e++) {
                mbar_wait_c(fb_, par);
                WG_FENCE();
                wgmma_ss_112<DAN, DW>(ac, ad, bd, 1);
                wgmma_ss_112<DAN, DW>(ac, ad + 256, bd + 16, 1);
                WG_COMMIT();
                WG_WAIT(1);
                warp_arrive(eb_);
                eb_ = fb_ + 8 * (B_EMPTY - B_FULL);
                ad += 1024; bd += 1024; fb_ += 8;
                if (e == 11 || e == 23) { ad -= 12 * 1024; bd -= 12 * 1024; fb_ -= 96; par = (par ^ 1) | sc; }
            }
            mbar_wait_cluster(BAR(B_PEER), sc);
            WG_WAIT(0);
            reg_fence<56>(ac);
            PROFC(24);
            uint32_t rdst, rbar;
            asm volatile("mapa.shared::cluster.u32 %0, %1, %2;" : "=r"(rdst) : "r"(sb + OFF_Y + (5 + w) * 16384 + t * 16), "r"(kh ^ 1 ^ sc));
            asm volatile("mapa.shared::cluster.u32 %0, %1, %2;" : "=r"(rbar) : "r"(BAR(B_XCH + w)), "r"(kh ^ 1 ^ sc));
#pragma unroll
            for (int g = 0; g < 7; g++) {
                const float v0 = ac[28 + 4 * g + 0], v1 = ac[28 + 4 * g + 1];
                const float v2 = ac[28 + 4 * g + 2], v3 = ac[28 + 4 * g + 3];
                if (!sc) asm volatile("st.async.shared::cluster.mbarrier::complete_tx::bytes.v4.f32 [%0], {%1,%2,%3,%4}, [%5];"
                             ::"r"(rdst + g * 2048), "f"(v0), "f"(v1), "f"(v2), "f"(v3), "r"(rbar) : "memory");
            }
            mbar_wait_cluster(BAR(B_XCH + w), sc);
            PROFC(25);
            uint32_t op[16];
#pragma unroll
            for (int g = 0; g < 7; g++) {
                const uint4 rv = *(const uint4*)(smem + OFF_Y + (5 + w) * 16384 + t * 16 + g * 2048);
                const float2 gb = *(const float2*)(smem + M_G + 224 + (8 * g + 2 * q) * 4);
                const float v0 = ac[4 * g + 0] + __uint_as_float(rv.x), v1 = ac[4 * g + 1] + __uint_as_float(rv.y);
                const float v2 = ac[4 * g + 2] + __uint_as_float(rv.z), v3 = ac[4 * g + 3] + __uint_as_float(rv.w);
                op[2 * g] = pack2(fmaf(gb.x, v0, bf_lo(x1p[2 * g])), fmaf(gb.y, v1, bf_hi(x1p[2 * g])));
                op[2 * g + 1] = pack2(fmaf(gb.x, v2, bf_lo(x1p[2 * g + 1])), fmaf(gb.y, v3, bf_hi(x1p[2 * g + 1])));
            }
            WAIT(B_EMPTY + 1, 0);
            const uint32_t oc = sb + OUT_STAGE + warp * 1792;
            const uint32_t oa = oc + (((lane >> 3) & 1) * 8 + (lane & 7)) * 112 + (lane >> 4) * 16;
            stsm4(oa, op[0], op[1], op[2], op[3]); stsm4(oa + 32, op[4], op[5], op[6], op[7]); stsm4(oa + 64, op[8], op[9], op[10], op[11]);
            asm volatile("stmatrix.sync.aligned.m8n8.x2.shared.b16 [%0], {%1,%2};" ::"r"(oa + 96), "r"(op[12]), "r"(op[13]));
            fence_async_smem();
            __syncwarp();
            asm volatile("{\n.reg .pred p;\nelect.sync _|p, 0xffffffff;\n@p cp.async.bulk.tensor.3d.global.shared::cta.bulk_group [%0, {%2, %3, %4}], [%1];\n"
                         "cp.async.bulk.commit_group;\ncp.async.bulk.wait_group.read 0;\n}" ::"l"(&p.om), "r"(oc), "r"(56 * j), "r"(128 * r + 64 * w + 16 * wi), "r"(0) : "memory");
        }
        PROFC(26);
        bar_sync(1 + w, 128);
        if (wi == 0) warp_arrive(BAR(B_DONE));
        return;
    }
    helper_late(p, r, j, warp PROF_ARGS);
}

#undef act
typedef CUresult (*EncodeFn)(CUtensorMap*, CUtensorMapDataType, cuuint32_t, void*, const cuuint64_t*, const cuuint64_t*, const cuuint32_t*,
                             const cuuint32_t*, CUtensorMapInterleave, CUtensorMapSwizzle, CUtensorMapL2promotion, CUtensorMapFloatOOBfill);

static void make_map(EncodeFn fn, CUtensorMap* m, const void* ptr, uint64_t d0, uint64_t d1, uint64_t d2, uint64_t s1, uint64_t s2,
                     uint32_t b0, uint32_t b1, uint32_t b2, CUtensorMapSwizzle sw) {
    cuuint64_t dims[3] = {d0, d1, d2}, strides[2] = {s1, s2};
    cuuint32_t box[3] = {b0, b1, b2}, es[3] = {1, 1, 1};
    CUresult rc = fn(m, CU_TENSOR_MAP_DATA_TYPE_BFLOAT16, 3, (void*)ptr, dims, strides, box, es, CU_TENSOR_MAP_INTERLEAVE_NONE, sw,
                     CU_TENSOR_MAP_L2_PROMOTION_L2_128B, CU_TENSOR_MAP_FLOAT_OOB_FILL_NONE);
    (void)rc;
}

extern "C" void kernel_launch(void* const* d_in, const int* in_sizes, int n_in, void* d_out, int out_size) {
    (void)in_sizes; (void)n_in; (void)out_size;
    static EncodeFn fn = nullptr;
    static uint32_t* act_base = nullptr;
    if (!fn) {
        cudaDriverEntryPointQueryResult st;
        cudaGetDriverEntryPoint("cuTensorMapEncodeTiled", (void**)&fn, cudaEnableDefault, &st);
        void* a = nullptr;
        cudaGetSymbolAddress(&a, g_act);
        act_base = (uint32_t*)(((uintptr_t)a + 0xFFFFF) & ~(uintptr_t)0xFFFFF);
        cudaFuncSetAttribute(fused_block_kernel, cudaFuncAttributeMaxDynamicSharedMemorySize, SMEM_BYTES);
    }
    Params p;
    p.x = (const bf16*)d_in[0];
    const bf16* wqkv = (const bf16*)d_in[1];
    p.wqkv = wqkv;
    p.wop = (const bf16*)d_in[2];
    p.wg = (const bf16*)d_in[4];
    p.wu = (const bf16*)d_in[5];
    p.wd = (const bf16*)d_in[6];
    p.c = (const bf16*)d_in[7];
    p.wmod = (const bf16*)d_in[8];
    p.out = (bf16*)d_out;
    p.zero = 0;
    p.actb = act_base;
    make_map(fn, &p.wm, p.wmod, 2688, 448, 1, 5376, 5376 * 448, 16, 224, 1, CU_TENSOR_MAP_SWIZZLE_NONE);
    make_map(fn, &p.wm2, p.wmod, 2688, 448, 1, 5376, 5376 * 448, 32, 224, 1, CU_TENSOR_MAP_SWIZZLE_NONE);
    make_map(fn, &p.om, p.out, 448, 2048, 1, 896, 896 * 2048, 56, 16, 1, CU_TENSOR_MAP_SWIZZLE_NONE);
    make_map(fn, &p.xm, p.x, 448, 2048, 1, 896, 896 * 2048, 64, 128, 1, CU_TENSOR_MAP_SWIZZLE_128B);
    make_map(fn, &p.qkv, wqkv, 1344, 448, 1, 2688, 2688 * 448, 64, 224, 1, CU_TENSOR_MAP_SWIZZLE_128B);
    make_map(fn, &p.wo, p.wop, 448, 448, 1, 896, 896 * 448, 64, 224, 1, CU_TENSOR_MAP_SWIZZLE_128B);
    make_map(fn, &p.ga, p.wg, 64, 448, 28, 3584, 128, 64, 32, 2, CU_TENSOR_MAP_SWIZZLE_128B);
    make_map(fn, &p.ua, p.wu, 64, 448, 28, 3584, 128, 64, 32, 2, CU_TENSOR_MAP_SWIZZLE_128B);
    make_map(fn, &p.gb, p.wg, 64, 448, 28, 3584, 128, 64, 64, 1, CU_TENSOR_MAP_SWIZZLE_128B);
    make_map(fn, &p.ub, p.wu, 64, 448, 28, 3584, 128, 64, 64, 1, CU_TENSOR_MAP_SWIZZLE_128B);
    make_map(fn, &p.gc, p.wg, 32, 448, 56, 3584, 64, 32, 64, 1, CU_TENSOR_MAP_SWIZZLE_64B);
    make_map(fn, &p.uc, p.wu, 32, 448, 56, 3584, 64, 32, 64, 1, CU_TENSOR_MAP_SWIZZLE_64B);
    make_map(fn, &p.dn, p.wd, 8, 1792, 56, 896, 16, 8, 32, 7, CU_TENSOR_MAP_SWIZZLE_NONE);
    fused_block_kernel<<<GRID, 384, SMEM_BYTES>>>(p);
}
```

```cpp
#include <cuda_runtime.h>
#include <cuda_bf16.h>
#include <cuda.h>
#include <stdint.h>

typedef __nv_bfloat16 bf16;

template<uint64_t CA, uint64_t CB> __device__ __forceinline__ void wgmma_sk_160(float* d, uint32_t da, uint32_t db, int sd) {
  asm volatile("{\n.reg .pred p;\n.reg .b64 a, b;\nsetp.ne.b32 p, %82, 0;\nmov.b64 a, {%80, %83};\nmov.b64 b, {%81, %84};\n"
    "wgmma.mma_async.sync.aligned.m64n160k16.f32.bf16.bf16 {%0,%1,%2,%3,%4,%5,%6,%7,%8,%9,%10,%11,%12,%13,%14,%15,%16,%17,%18,%19,%20,%21,%22,%23,%24,%25,%26,%27,%28,%29,%30,%31,%32,%33,%34,%35,%36,%37,%38,%39,%40,%41,%42,%43,%44,%45,%46,%47,%48,%49,%50,%51,%52,%53,%54,%55,%56,%57,%58,%59,%60,%61,%62,%63,%64,%65,%66,%67,%68,%69,%70,%71,%72,%73,%74,%75,%76,%77,%78,%79}, a, b, p, 1, 1, 0, 0;\n}\n"
    : "+f"(d[0]),"+f"(d[1]),"+f"(d[2]),"+f"(d[3]),"+f"(d[4]),"+f"(d[5]),"+f"(d[6]),"+f"(d[7]),"+f"(d[8]),"+f"(d[9]),"+f"(d[10]),"+f"(d[11]),"+f"(d[12]),"+f"(d[13]),"+f"(d[14]),"+f"(d[15]),"+f"(d[16]),"+f"(d[17]),"+f"(d[18]),"+f"(d[19]),"+f"(d[20]),"+f"(d[21]),"+f"(d[22]),"+f"(d[23]),"+f"(d[24]),"+f"(d[25]),"+f"(d[26]),"+f"(d[27]),"+f"(d[28]),"+f"(d[29]),"+f"(d[30]),"+f"(d[31]),"+f"(d[32]),"+f"(d[33]),"+f"(d[34]),"+f"(d[35]),"+f"(d[36]),"+f"(d[37]),"+f"(d[38]),"+f"(d[39]),"+f"(d[40]),"+f"(d[41]),"+f"(d[42]),"+f"(d[43]),"+f"(d[44]),"+f"(d[45]),"+f"(d[46]),"+f"(d[47]),"+f"(d[48]),"+f"(d[49]),"+f"(d[50]),"+f"(d[51]),"+f"(d[52]),"+f"(d[53]),"+f"(d[54]),"+f"(d[55]),"+f"(d[56]),"+f"(d[57]),"+f"(d[58]),"+f"(d[59]),"+f"(d[60]),"+f"(d[61]),"+f"(d[62]),"+f"(d[63]),"+f"(d[64]),"+f"(d[65]),"+f"(d[66]),"+f"(d[67]),"+f"(d[68]),"+f"(d[69]),"+f"(d[70]),"+f"(d[71]),"+f"(d[72]),"+f"(d[73]),"+f"(d[74]),"+f"(d[75]),"+f"(d[76]),"+f"(d[77]),"+f"(d[78]),"+f"(d[79])
    : "r"(da), "r"(db), "r"(sd), "n"((uint32_t)(CA >> 32)), "n"((uint32_t)(CB >> 32)));
}
__device__ __forceinline__ void wgmma_rl_56(float* d, uint32_t a0, uint32_t a1, uint32_t a2, uint32_t a3, uint64_t db, int sd) {
  asm volatile("{\n.reg .pred p;\nsetp.ne.b32 p, %33, 0;\n"
    "wgmma.mma_async.sync.aligned.m64n56k16.f32.bf16.bf16 {%0,%1,%2,%3,%4,%5,%6,%7,%8,%9,%10,%11,%12,%13,%14,%15,%16,%17,%18,%19,%20,%21,%22,%23,%24,%25,%26,%27}, {%28,%29,%30,%31}, %32, p, 1, 1, 1;\n}\n"
    : "+f"(d[0]),"+f"(d[1]),"+f"(d[2]),"+f"(d[3]),"+f"(d[4]),"+f"(d[5]),"+f"(d[6]),"+f"(d[7]),"+f"(d[8]),"+f"(d[9]),"+f"(d[10]),"+f"(d[11]),"+f"(d[12]),"+f"(d[13]),"+f"(d[14]),"+f"(d[15]),"+f"(d[16]),"+f"(d[17]),"+f"(d[18]),"+f"(d[19]),"+f"(d[20]),"+f"(d[21]),"+f"(d[22]),"+f"(d[23]),"+f"(d[24]),"+f"(d[25]),"+f"(d[26]),"+f"(d[27])
    : "r"(a0), "r"(a1), "r"(a2), "r"(a3), "l"(db), "r"(sd));
}
template<uint64_t CA, uint64_t CB> __device__ __forceinline__ void wgmma_ss_56(float* d, uint32_t da, uint32_t db, int sd) {
  asm volatile("{\n.reg .pred p;\n.reg .b64 a, b;\nsetp.ne.b32 p, %30, 0;\nmov.b64 a, {%28, %31};\nmov.b64 b, {%29, %32};\n"
    "wgmma.mma_async.sync.aligned.m64n56k16.f32.bf16.bf16 {%0,%1,%2,%3,%4,%5,%6,%7,%8,%9,%10,%11,%12,%13,%14,%15,%16,%17,%18,%19,%20,%21,%22,%23,%24,%25,%26,%27}, a, b, p, 1, 1, 0, 1;\n}\n"
    : "+f"(d[0]),"+f"(d[1]),"+f"(d[2]),"+f"(d[3]),"+f"(d[4]),"+f"(d[5]),"+f"(d[6]),"+f"(d[7]),"+f"(d[8]),"+f"(d[9]),"+f"(d[10]),"+f"(d[11]),"+f"(d[12]),"+f"(d[13]),"+f"(d[14]),"+f"(d[15]),"+f"(d[16]),"+f"(d[17]),"+f"(d[18]),"+f"(d[19]),"+f"(d[20]),"+f"(d[21]),"+f"(d[22]),"+f"(d[23]),"+f"(d[24]),"+f"(d[25]),"+f"(d[26]),"+f"(d[27])
    : "r"(da), "r"(db), "r"(sd), "n"((uint32_t)(CA >> 32)), "n"((uint32_t)(CB >> 32)));
}
__device__ __forceinline__ void wgmma_rl_256(float* d, uint32_t a0, uint32_t a1, uint32_t a2, uint32_t a3, uint64_t db, int sd) {
  asm volatile("{\n.reg .pred p;\nsetp.ne.b32 p, %133, 0;\n"
    "wgmma.mma_async.sync.aligned.m64n256k16.f32.bf16.bf16 {%0,%1,%2,%3,%4,%5,%6,%7,%8,%9,%10,%11,%12,%13,%14,%15,%16,%17,%18,%19,%20,%21,%22,%23,%24,%25,%26,%27,%28,%29,%30,%31,%32,%33,%34,%35,%36,%37,%38,%39,%40,%41,%42,%43,%44,%45,%46,%47,%48,%49,%50,%51,%52,%53,%54,%55,%56,%57,%58,%59,%60,%61,%62,%63,%64,%65,%66,%67,%68,%69,%70,%71,%72,%73,%74,%75,%76,%77,%78,%79,%80,%81,%82,%83,%84,%85,%86,%87,%88,%89,%90,%91,%92,%93,%94,%95,%96,%97,%98,%99,%100,%101,%102,%103,%104,%105,%106,%107,%108,%109,%110,%111,%112,%113,%114,%115,%116,%117,%118,%119,%120,%121,%122,%123,%124,%125,%126,%127}, {%128,%129,%130,%131}, %132, p, 1, 1, 1;\n}\n"
    : "+f"(d[0]),"+f"(d[1]),"+f"(d[2]),"+f"(d[3]),"+f"(d[4]),"+f"(d[5]),"+f"(d[6]),"+f"(d[7]),"+f"(d[8]),"+f"(d[9]),"+f"(d[10]),"+f"(d[11]),"+f"(d[12]),"+f"(d[13]),"+f"(d[14]),"+f"(d[15]),"+f"(d[16]),"+f"(d[17]),"+f"(d[18]),"+f"(d[19]),"+f"(d[20]),"+f"(d[21]),"+f"(d[22]),"+f"(d[23]),"+f"(d[24]),"+f"(d[25]),"+f"(d[26]),"+f"(d[27]),"+f"(d[28]),"+f"(d[29]),"+f"(d[30]),"+f"(d[31]),"+f"(d[32]),"+f"(d[33]),"+f"(d[34]),"+f"(d[35]),"+f"(d[36]),"+f"(d[37]),"+f"(d[38]),"+f"(d[39]),"+f"(d[40]),"+f"(d[41]),"+f"(d[42]),"+f"(d[43]),"+f"(d[44]),"+f"(d[45]),"+f"(d[46]),"+f"(d[47]),"+f"(d[48]),"+f"(d[49]),"+f"(d[50]),"+f"(d[51]),"+f"(d[52]),"+f"(d[53]),"+f"(d[54]),"+f"(d[55]),"+f"(d[56]),"+f"(d[57]),"+f"(d[58]),"+f"(d[59]),"+f"(d[60]),"+f"(d[61]),"+f"(d[62]),"+f"(d[63]),"+f"(d[64]),"+f"(d[65]),"+f"(d[66]),"+f"(d[67]),"+f"(d[68]),"+f"(d[69]),"+f"(d[70]),"+f"(d[71]),"+f"(d[72]),"+f"(d[73]),"+f"(d[74]),"+f"(d[75]),"+f"(d[76]),"+f"(d[77]),"+f"(d[78]),"+f"(d[79]),"+f"(d[80]),"+f"(d[81]),"+f"(d[82]),"+f"(d[83]),"+f"(d[84]),"+f"(d[85]),"+f"(d[86]),"+f"(d[87]),"+f"(d[88]),"+f"(d[89]),"+f"(d[90]),"+f"(d[91]),"+f"(d[92]),"+f"(d[93]),"+f"(d[94]),"+f"(d[95]),"+f"(d[96]),"+f"(d[97]),"+f"(d[98]),"+f"(d[99]),"+f"(d[100]),"+f"(d[101]),"+f"(d[102]),"+f"(d[103]),"+f"(d[104]),"+f"(d[105]),"+f"(d[106]),"+f"(d[107]),"+f"(d[108]),"+f"(d[109]),"+f"(d[110]),"+f"(d[111]),"+f"(d[112]),"+f"(d[113]),"+f"(d[114]),"+f"(d[115]),"+f"(d[116]),"+f"(d[117]),"+f"(d[118]),"+f"(d[119]),"+f"(d[120]),"+f"(d[121]),"+f"(d[122]),"+f"(d[123]),"+f"(d[124]),"+f"(d[125]),"+f"(d[126]),"+f"(d[127])
    : "r"(a0), "r"(a1), "r"(a2), "r"(a3), "l"(db), "r"(sd));
}
template<uint64_t CA, uint64_t CB> __device__ __forceinline__ void wgmma_ss_128(float* d, uint32_t da, uint32_t db, int sd) {
  asm volatile("{\n.reg .pred p;\n.reg .b64 a, b;\nsetp.ne.b32 p, %66, 0;\nmov.b64 a, {%64, %67};\nmov.b64 b, {%65, %68};\n"
    "wgmma.mma_async.sync.aligned.m64n128k16.f32.bf16.bf16 {%0,%1,%2,%3,%4,%5,%6,%7,%8,%9,%10,%11,%12,%13,%14,%15,%16,%17,%18,%19,%20,%21,%22,%23,%24,%25,%26,%27,%28,%29,%30,%31,%32,%33,%34,%35,%36,%37,%38,%39,%40,%41,%42,%43,%44,%45,%46,%47,%48,%49,%50,%51,%52,%53,%54,%55,%56,%57,%58,%59,%60,%61,%62,%63}, a, b, p, 1, 1, 0, 1;\n}\n"
    : "+f"(d[0]),"+f"(d[1]),"+f"(d[2]),"+f"(d[3]),"+f"(d[4]),"+f"(d[5]),"+f"(d[6]),"+f"(d[7]),"+f"(d[8]),"+f"(d[9]),"+f"(d[10]),"+f"(d[11]),"+f"(d[12]),"+f"(d[13]),"+f"(d[14]),"+f"(d[15]),"+f"(d[16]),"+f"(d[17]),"+f"(d[18]),"+f"(d[19]),"+f"(d[20]),"+f"(d[21]),"+f"(d[22]),"+f"(d[23]),"+f"(d[24]),"+f"(d[25]),"+f"(d[26]),"+f"(d[27]),"+f"(d[28]),"+f"(d[29]),"+f"(d[30]),"+f"(d[31]),"+f"(d[32]),"+f"(d[33]),"+f"(d[34]),"+f"(d[35]),"+f"(d[36]),"+f"(d[37]),"+f"(d[38]),"+f"(d[39]),"+f"(d[40]),"+f"(d[41]),"+f"(d[42]),"+f"(d[43]),"+f"(d[44]),"+f"(d[45]),"+f"(d[46]),"+f"(d[47]),"+f"(d[48]),"+f"(d[49]),"+f"(d[50]),"+f"(d[51]),"+f"(d[52]),"+f"(d[53]),"+f"(d[54]),"+f"(d[55]),"+f"(d[56]),"+f"(d[57]),"+f"(d[58]),"+f"(d[59]),"+f"(d[60]),"+f"(d[61]),"+f"(d[62]),"+f"(d[63])
    : "r"(da), "r"(db), "r"(sd), "n"((uint32_t)(CA >> 32)), "n"((uint32_t)(CB >> 32)));
}
template<uint64_t CA, uint64_t CB> __device__ __forceinline__ void wgmma_ss_64(float* d, uint32_t da, uint32_t db, int sd) {
  asm volatile("{\n.reg .pred p;\n.reg .b64 a, b;\nsetp.ne.b32 p, %34, 0;\nmov.b64 a, {%32, %35};\nmov.b64 b, {%33, %36};\n"
    "wgmma.mma_async.sync.aligned.m64n64k16.f32.bf16.bf16 {%0,%1,%2,%3,%4,%5,%6,%7,%8,%9,%10,%11,%12,%13,%14,%15,%16,%17,%18,%19,%20,%21,%22,%23,%24,%25,%26,%27,%28,%29,%30,%31}, a, b, p, 1, 1, 0, 1;\n}\n"
    : "+f"(d[0]),"+f"(d[1]),"+f"(d[2]),"+f"(d[3]),"+f"(d[4]),"+f"(d[5]),"+f"(d[6]),"+f"(d[7]),"+f"(d[8]),"+f"(d[9]),"+f"(d[10]),"+f"(d[11]),"+f"(d[12]),"+f"(d[13]),"+f"(d[14]),"+f"(d[15]),"+f"(d[16]),"+f"(d[17]),"+f"(d[18]),"+f"(d[19]),"+f"(d[20]),"+f"(d[21]),"+f"(d[22]),"+f"(d[23]),"+f"(d[24]),"+f"(d[25]),"+f"(d[26]),"+f"(d[27]),"+f"(d[28]),"+f"(d[29]),"+f"(d[30]),"+f"(d[31])
    : "r"(da), "r"(db), "r"(sd), "n"((uint32_t)(CA >> 32)), "n"((uint32_t)(CB >> 32)));
}
template<uint64_t CA, uint64_t CB> __device__ __forceinline__ void wgmma_ss_112(float* d, uint32_t da, uint32_t db, int sd) {
  asm volatile("{\n.reg .pred p;\n.reg .b64 a, b;\nsetp.ne.b32 p, %58, 0;\nmov.b64 a, {%56, %59};\nmov.b64 b, {%57, %60};\n"
    "wgmma.mma_async.sync.aligned.m64n112k16.f32.bf16.bf16 {%0,%1,%2,%3,%4,%5,%6,%7,%8,%9,%10,%11,%12,%13,%14,%15,%16,%17,%18,%19,%20,%21,%22,%23,%24,%25,%26,%27,%28,%29,%30,%31,%32,%33,%34,%35,%36,%37,%38,%39,%40,%41,%42,%43,%44,%45,%46,%47,%48,%49,%50,%51,%52,%53,%54,%55}, a, b, p, 1, 1, 0, 1;\n}\n"
    : "+f"(d[0]),"+f"(d[1]),"+f"(d[2]),"+f"(d[3]),"+f"(d[4]),"+f"(d[5]),"+f"(d[6]),"+f"(d[7]),"+f"(d[8]),"+f"(d[9]),"+f"(d[10]),"+f"(d[11]),"+f"(d[12]),"+f"(d[13]),"+f"(d[14]),"+f"(d[15]),"+f"(d[16]),"+f"(d[17]),"+f"(d[18]),"+f"(d[19]),"+f"(d[20]),"+f"(d[21]),"+f"(d[22]),"+f"(d[23]),"+f"(d[24]),"+f"(d[25]),"+f"(d[26]),"+f"(d[27]),"+f"(d[28]),"+f"(d[29]),"+f"(d[30]),"+f"(d[31]),"+f"(d[32]),"+f"(d[33]),"+f"(d[34]),"+f"(d[35]),"+f"(d[36]),"+f"(d[37]),"+f"(d[38]),"+f"(d[39]),"+f"(d[40]),"+f"(d[41]),"+f"(d[42]),"+f"(d[43]),"+f"(d[44]),"+f"(d[45]),"+f"(d[46]),"+f"(d[47]),"+f"(d[48]),"+f"(d[49]),"+f"(d[50]),"+f"(d[51]),"+f"(d[52]),"+f"(d[53]),"+f"(d[54]),"+f"(d[55])
    : "r"(da), "r"(db), "r"(sd), "n"((uint32_t)(CA >> 32)), "n"((uint32_t)(CB >> 32)));
}
template<uint64_t CB> __device__ __forceinline__ void wgmma_rs_112(float* d, uint32_t a0, uint32_t a1, uint32_t a2, uint32_t a3, uint32_t db, int sd) {
  asm volatile("{\n.reg .pred p;\n.reg .b64 b;\nsetp.ne.b32 p, %61, 0;\nmov.b64 b, {%60, %62};\n"
    "wgmma.mma_async.sync.aligned.m64n112k16.f32.bf16.bf16 {%0,%1,%2,%3,%4,%5,%6,%7,%8,%9,%10,%11,%12,%13,%14,%15,%16,%17,%18,%19,%20,%21,%22,%23,%24,%25,%26,%27,%28,%29,%30,%31,%32,%33,%34,%35,%36,%37,%38,%39,%40,%41,%42,%43,%44,%45,%46,%47,%48,%49,%50,%51,%52,%53,%54,%55}, {%56,%57,%58,%59}, b, p, 1, 1, 1;\n}\n"
    : "+f"(d[0]),"+f"(d[1]),"+f"(d[2]),"+f"(d[3]),"+f"(d[4]),"+f"(d[5]),"+f"(d[6]),"+f"(d[7]),"+f"(d[8]),"+f"(d[9]),"+f"(d[10]),"+f"(d[11]),"+f"(d[12]),"+f"(d[13]),"+f"(d[14]),"+f"(d[15]),"+f"(d[16]),"+f"(d[17]),"+f"(d[18]),"+f"(d[19]),"+f"(d[20]),"+f"(d[21]),"+f"(d[22]),"+f"(d[23]),"+f"(d[24]),"+f"(d[25]),"+f"(d[26]),"+f"(d[27]),"+f"(d[28]),"+f"(d[29]),"+f"(d[30]),"+f"(d[31]),"+f"(d[32]),"+f"(d[33]),"+f"(d[34]),"+f"(d[35]),"+f"(d[36]),"+f"(d[37]),"+f"(d[38]),"+f"(d[39]),"+f"(d[40]),"+f"(d[41]),"+f"(d[42]),"+f"(d[43]),"+f"(d[44]),"+f"(d[45]),"+f"(d[46]),"+f"(d[47]),"+f"(d[48]),"+f"(d[49]),"+f"(d[50]),"+f"(d[51]),"+f"(d[52]),"+f"(d[53]),"+f"(d[54]),"+f"(d[55])
    : "r"(a0), "r"(a1), "r"(a2), "r"(a3), "r"(db), "r"(sd), "n"((uint32_t)(CB >> 32)));
}

constexpr int DM = 448;
constexpr int NCTA = 128;
#define MAPPING 1
#define GRID 128
#define PINGPONG 0
#define WIN 6
#define WIN_END 25
#define UNR_B 1
#define UNR_C 1
constexpr int kB = UNR_B, kC = UNR_C;
#define LIKELY(x) __builtin_expect(!!(x), 1)
#define PACE 1
#define PACE_END 6
#define GEMV_AT 0
#define NPRE 14
#define ATT_OFF 0
#define ATT_WG 1
#define XFIRST 7
#define KDELAY 0
#define KEARLY 1
#define VPRE 3
#define VGATE 2
#define LNMODE 0
#define WSWAP 1
#define ASYM 1
#define MAP_S 4
constexpr int SPIN_LIMIT = 1 << 22;

constexpr uint32_t OFF_X = 0, OFF_Y = 114688, OFF_MISC = 229376, SMEM_BYTES = 232448;
constexpr uint32_t Y_VR = 0, Y_K = 28672, Y_KOWN = 57344, Y_VOWN = 71680, Y_Q = 86016;
constexpr uint32_t HALF = 57344;
constexpr uint32_t X_STAT = 49152;
constexpr uint32_t OUT_STAGE = 5 * 16384;
constexpr uint32_t M_BAR = OFF_MISC;
constexpr uint32_t M_ST = OFF_MISC + 512;
constexpr uint32_t M_G = OFF_MISC + 2304;
constexpr uint32_t M_EPOCH = OFF_MISC + 3040;
enum { B_XFULL = 0, B_FULLK = 7, B_FULLV = 8, B_FULLQ, B_KRFULL, B_VRFULL, B_WOFULL, B_XCH, B_MOD1 = 15, B_FULL = 16, B_WMFULL = 30,
       B_EMPTY = 32, B_XFREE = B_EMPTY + 12, B_GEMV, B_PEER,
       B_PUB = 47,
       B_WMFREE = 56, B_HRDY, B_GFULL = B_HRDY + 3, B_DONE = 31, B_DUMMY = B_GEMV };

__device__ uint32_t g_ticket;
__device__ __align__(128) uint32_t g_mod[8 * 6 * DM];
__device__ __align__(128) uint32_t g_flag[144 * 128];
constexpr int RB_WORDS = 262144, RB_KV = 0, RB_O = 57344, RB_X1 = 86016, RB_H2 = 143360, RB_ST = 258048;
__device__ __align__(128) uint32_t g_act[18 * RB_WORDS];
__device__ __align__(128) uint32_t g_wd[56 * 4 * 1792];
#define PROFH(id)
#define PROFH1(id)
#define PROFC(id)

struct alignas(64) Params {
    CUtensorMap wm, wm2, om, xm, qkv, wo, ga, ua, gb, ub, gc, uc, dn;
    const bf16 *x, *c, *wqkv, *wmod, *wg, *wu, *wd, *wop;
    bf16* out;
    uint32_t* actb;
    uint32_t zero;
};

__device__ __forceinline__ void mbar_init(uint32_t bar, int cnt) { asm volatile("mbarrier.init.shared::cta.b64 [%0], %1;" ::"r"(bar), "r"(cnt) : "memory"); }
__device__ __forceinline__ void mbar_expect_tx(uint32_t bar, uint32_t bytes) { asm volatile("mbarrier.arrive.expect_tx.shared::cta.b64 _, [%0], %1;" ::"r"(bar), "r"(bytes) : "memory"); }
__device__ __forceinline__ void mbar_arrive(uint32_t bar) { asm volatile("mbarrier.arrive.shared::cta.b64 _, [%0];" ::"r"(bar) : "memory"); }
__device__ __forceinline__ void mbar_wait(uint32_t bar, uint32_t parity) {
    uint32_t ok; int n = 0;
    do {
        asm volatile("{\n.reg .pred p;\nmbarrier.try_wait.parity.shared::cta.b64 p, [%1], %2;\nselp.u32 %0, 1, 0, p;\n}" : "=r"(ok) : "r"(bar), "r"(parity) : "memory");
        if (++n > SPIN_LIMIT) __trap();
    } while (!ok);
}
__device__ __forceinline__ void mbar_wait_c(uint32_t bar, uint32_t parity) {
    asm volatile("{\n.reg .pred p;\nWL:\nmbarrier.try_wait.parity.shared::cta.b64 p, [%0], %1, 0x989680;\n@!p bra WL;\n}" ::"r"(bar), "r"(parity) : "memory");
}
__device__ __forceinline__ void mbar_wait_cluster(uint32_t bar, uint32_t parity) {
    asm volatile("{\n.reg .pred p;\nWL:\nmbarrier.try_wait.parity.acquire.cluster.shared::cta.b64 p, [%0], %1, 0x989680;\n@!p bra WL;\n}" ::"r"(bar), "r"(parity) : "memory");
}
__device__ __forceinline__ void warp_arrive(uint32_t bar) {
    __syncwarp();
    asm volatile("{\n.reg .pred p;\nelect.sync _|p, 0xffffffff;\n@p mbarrier.arrive.shared::cta.b64 _, [%0];\n}" ::"r"(bar) : "memory");
}
__device__ __forceinline__ int opaque(int v) { return __shfl_sync(~0u, v, 0); }
__device__ __forceinline__ int fresh_tid() { int v; asm volatile("mov.u32 %0, %%tid.x;" : "=r"(v)); return v; }
__device__ __forceinline__ void bar_sync(int id, int n) { asm volatile("bar.sync %0, %1;" ::"r"(id), "r"(n) : "memory"); }
__device__ __forceinline__ void bar_arrive(int id, int n) { asm volatile("bar.arrive %0, %1;" ::"r"(id), "r"(n) : "memory"); }
__device__ __forceinline__ void fence_async_smem() { asm volatile("fence.proxy.async.shared::cta;" ::: "memory"); }
__device__ __forceinline__ void fence_async_global() { asm volatile("fence.proxy.async.global;" ::: "memory"); }
__device__ __forceinline__ void fence_gpu() { asm volatile("fence.release.gpu;" ::: "memory"); }
__device__ __forceinline__ void tma3(uint32_t dst, const CUtensorMap* m, int c0, int c1, int c2, uint32_t bar) {
    asm volatile("cp.async.bulk.tensor.3d.shared::cluster.global.mbarrier::complete_tx::bytes [%0], [%1, {%3, %4, %5}], [%2];"
                 ::"r"(dst), "l"(m), "r"(bar), "r"(c0), "r"(c1), "r"(c2) : "memory");
}
__device__ __forceinline__ void bulk_load(uint32_t dst, const void* src, uint32_t bytes, uint32_t bar) {
    asm volatile("cp.async.bulk.shared::cluster.global.mbarrier::complete_tx::bytes [%0], [%1], %2, [%3];" ::"r"(dst), "l"(src), "r"(bytes), "r"(bar) : "memory");
}
__device__ __forceinline__ void expect_e(uint32_t bar, uint32_t bytes) {
    asm volatile("{\n.reg .pred p;\nelect.sync _|p, 0xffffffff;\n@p mbarrier.arrive.expect_tx.shared::cta.b64 _, [%0], %1;\n}" ::"r"(bar), "r"(bytes) : "memory");
}
__device__ __forceinline__ void tma3_e(uint32_t dst, const CUtensorMap* m, int c0, int c1, int c2, uint32_t bar) {
    asm volatile("{\n.reg .pred p;\nelect.sync _|p, 0xffffffff;\n@p cp.async.bulk.tensor.3d.shared::cluster.global.mbarrier::complete_tx::bytes [%0], [%1, {%3, %4, %5}], [%2];\n}"
                 ::"r"(dst), "l"(m), "r"(bar), "r"(c0), "r"(c1), "r"(c2) : "memory");
}
__device__ __forceinline__ void bulk_e(uint32_t dst, const void* src, uint32_t bytes, uint32_t bar) {
    asm volatile("{\n.reg .pred p;\nelect.sync _|p, 0xffffffff;\n@p cp.async.bulk.shared::cluster.global.mbarrier::complete_tx::bytes [%0], [%1], %2, [%3];\n}"
                 ::"r"(dst), "l"(src), "r"(bytes), "r"(bar) : "memory");
}
__device__ __forceinline__ void init_e(uint32_t bar, int cnt) {
    asm volatile("{\n.reg .pred p;\nelect.sync _|p, 0xffffffff;\n@p mbarrier.init.shared::cta.b64 [%0], %1;\n}" ::"r"(bar), "r"(cnt) : "memory");
}
__device__ __forceinline__ void l2_prefetch_e(const void* src, uint32_t bytes) {
    asm volatile("{\n.reg .pred p;\nelect.sync _|p, 0xffffffff;\n@p cp.async.bulk.prefetch.L2.global [%0], %1;\n}" ::"l"(src), "r"(bytes) : "memory");
}
__device__ __forceinline__ uint32_t ld_relaxed(const uint32_t* p) { uint32_t v; asm volatile("ld.relaxed.gpu.global.u32 %0, [%1];" : "=r"(v) : "l"(p) : "memory"); return v; }
__device__ __forceinline__ void st_relaxed(uint32_t* p, uint32_t v) { asm volatile("st.relaxed.gpu.global.u32 [%0], %1;" ::"l"(p), "r"(v) : "memory"); }
__device__ __forceinline__ uint4 ld_relaxed4(const uint4* p) { uint4 v; asm volatile("ld.relaxed.gpu.global.v4.u32 {%0,%1,%2,%3}, [%4];" : "=r"(v.x), "=r"(v.y), "=r"(v.z), "=r"(v.w) : "l"(p) : "memory"); return v; }
__device__ __forceinline__ void st_relaxed4(uint4* p, uint4 v) { asm volatile("st.relaxed.gpu.global.v4.u32 [%0], {%1,%2,%3,%4};" ::"l"(p), "r"(v.x), "r"(v.y), "r"(v.z), "r"(v.w) : "memory"); }
__device__ __forceinline__ uint4 ldg_nc4(const void* p) { uint4 v; asm volatile("ld.global.nc.L1::no_allocate.v4.u32 {%0,%1,%2,%3}, [%4];" : "=r"(v.x), "=r"(v.y), "=r"(v.z), "=r"(v.w) : "l"(p)); return v; }
__device__ __forceinline__ uint32_t ldg_nc(const void* p) { uint32_t v; asm volatile("ld.global.nc.u32 %0, [%1];" : "=r"(v) : "l"(p)); return v; }
__device__ __forceinline__ uint32_t ld_acquire(const uint32_t* p) { uint32_t v; asm volatile("ld.acquire.gpu.global.u32 %0, [%1];" : "=r"(v) : "l"(p) : "memory"); return v; }
__device__ __forceinline__ uint4 lds4(uint32_t a) { uint4 v; asm volatile("ld.shared.v4.u32 {%0,%1,%2,%3}, [%4];" : "=r"(v.x), "=r"(v.y), "=r"(v.z), "=r"(v.w) : "r"(a) : "memory"); return v; }
__device__ __forceinline__ float2 lds2f(uint32_t a) { float2 v; asm volatile("ld.shared.v2.f32 {%0,%1}, [%2];" : "=f"(v.x), "=f"(v.y) : "r"(a) : "memory"); return v; }
__device__ __forceinline__ uint32_t lds1(uint32_t a) { uint32_t v; asm volatile("ld.shared.u32 %0, [%1];" : "=r"(v) : "r"(a) : "memory"); return v; }
__device__ __forceinline__ void sts4(uint32_t a, uint4 v) { asm volatile("st.shared.v4.u32 [%0], {%1,%2,%3,%4};" ::"r"(a), "r"(v.x), "r"(v.y), "r"(v.z), "r"(v.w) : "memory"); }
__device__ __forceinline__ void sts2(uint32_t a, uint32_t x, uint32_t y) { asm volatile("st.shared.v2.u32 [%0], {%1,%2};" ::"r"(a), "r"(x), "r"(y) : "memory"); }
__device__ __forceinline__ void sts1(uint32_t a, uint32_t v) { asm volatile("st.shared.u32 [%0], %1;" ::"r"(a), "r"(v) : "memory"); }
__device__ __forceinline__ void stsm4(uint32_t a, uint32_t r0, uint32_t r1, uint32_t r2, uint32_t r3) {
    asm volatile("stmatrix.sync.aligned.m8n8.x4.shared.b16 [%0], {%1,%2,%3,%4};" ::"r"(a), "r"(r0), "r"(r1), "r"(r2), "r"(r3));
}
__device__ __forceinline__ uint32_t pack2(float lo, float hi) { uint32_t r; asm("cvt.rn.bf16x2.f32 %0, %1, %2;" : "=r"(r) : "f"(hi), "f"(lo)); return r; }
__device__ __forceinline__ uint32_t pack2_relu(float lo, float hi) { uint32_t r; asm("cvt.rn.relu.bf16x2.f32 %0, %1, %2;" : "=r"(r) : "f"(hi), "f"(lo)); return r; }
__device__ __forceinline__ uint32_t hfma2(uint32_t a, uint32_t b, uint32_t c) { uint32_t r; asm("fma.rn.bf16x2 %0, %1, %2, %3;" : "=r"(r) : "r"(a), "r"(b), "r"(c)); return r; }
__device__ __forceinline__ uint32_t hmul2(uint32_t a, uint32_t b) { uint32_t r; asm("mul.rn.bf16x2 %0, %1, %2;" : "=r"(r) : "r"(a), "r"(b)); return r; }
__device__ __forceinline__ float bf_lo(uint32_t v) { return __uint_as_float(v << 16); }
__device__ __forceinline__ float bf_hi(uint32_t v) { return __uint_as_float(v & 0xFFFF0000u); }
__device__ __forceinline__ float bf_round(float v) { return bf_lo(pack2(v, 0.f)); }
__device__ __forceinline__ float ex2(float x) { float r; asm("ex2.approx.ftz.f32 %0, %1;" : "=f"(r) : "f"(x)); return r; }
__device__ __forceinline__ void mma16816(float* d, uint32_t a0, uint32_t a1, uint32_t a2, uint32_t a3, uint32_t b0, uint32_t b1) {
    asm("mma.sync.aligned.m16n8k16.row.col.f32.bf16.bf16.f32 {%0,%1,%2,%3}, {%4,%5,%6,%7}, {%8,%9}, {%0,%1,%2,%3};"
        : "+f"(d[0]), "+f"(d[1]), "+f"(d[2]), "+f"(d[3]) : "r"(a0), "r"(a1), "r"(a2), "r"(a3), "r"(b0), "r"(b1));
}
__device__ __forceinline__ void mma16816_first(float* d, uint32_t a0, uint32_t a1, uint32_t a2, uint32_t a3, uint32_t b0, uint32_t b1) {
    asm volatile("mma.sync.aligned.m16n8k16.row.col.f32.bf16.bf16.f32 {%0,%1,%2,%3}, {%4,%5,%6,%7}, {%8,%9}, {%10,%10,%10,%10};"
        : "=f"(d[0]), "=f"(d[1]), "=f"(d[2]), "=f"(d[3]) : "r"(a0), "r"(a1), "r"(a2), "r"(a3), "r"(b0), "r"(b1), "f"(0.f));
}
__device__ __forceinline__ void mma16816_v(float* d, uint32_t a0, uint32_t a1, uint32_t a2, uint32_t a3, uint32_t b0, uint32_t b1) {
    asm volatile("mma.sync.aligned.m16n8k16.row.col.f32.bf16.bf16.f32 {%0,%1,%2,%3}, {%4,%5,%6,%7}, {%8,%9}, {%0,%1,%2,%3};"
        : "+f"(d[0]), "+f"(d[1]), "+f"(d[2]), "+f"(d[3]) : "r"(a0), "r"(a1), "r"(a2), "r"(a3), "r"(b0), "r"(b1));
}
__device__ __forceinline__ void mma1688(float* d, uint32_t a0, uint32_t a1, uint32_t b0) {
    asm("mma.sync.aligned.m16n8k8.row.col.f32.bf16.bf16.f32 {%0,%1,%2,%3}, {%4,%5}, {%6}, {%0,%1,%2,%3};"
        : "+f"(d[0]), "+f"(d[1]), "+f"(d[2]), "+f"(d[3]) : "r"(a0), "r"(a1), "r"(b0));
}
__device__ __forceinline__ void ldsm4(uint32_t a, uint32_t* r) {
    asm volatile("ldmatrix.sync.aligned.m8n8.x4.shared.b16 {%0,%1,%2,%3}, [%4];" : "=r"(r[0]), "=r"(r[1]), "=r"(r[2]), "=r"(r[3]) : "r"(a));
}
__device__ __forceinline__ void ldsm4t(uint32_t a, uint32_t* r) {
    asm volatile("ldmatrix.sync.aligned.m8n8.x4.trans.shared.b16 {%0,%1,%2,%3}, [%4];" : "=r"(r[0]), "=r"(r[1]), "=r"(r[2]), "=r"(r[3]) : "r"(a));
}
__device__ __forceinline__ uint32_t nz(uint32_t v) { uint32_t r; asm("max.u32 %0, %1, 1;" : "=r"(r) : "r"(v)); return r; }
__device__ __forceinline__ float rcp(float x) { float r; asm("rcp.approx.ftz.f32 %0, %1;" : "=f"(r) : "f"(x)); return r; }
__device__ __forceinline__ uint2 ld_relaxed2(const void* p) { uint2 v; asm volatile("ld.relaxed.gpu.global.v2.u32 {%0,%1}, [%2];" : "=r"(v.x), "=r"(v.y) : "l"(p) : "memory"); return v; }
__device__ __forceinline__ void st_relaxed2(void* p, uint32_t x, uint32_t y) { asm volatile("st.relaxed.gpu.global.v2.u32 [%0], {%1,%2};" ::"l"(p), "r"(max(x, 1u)), "r"(max(y, 1u)) : "memory"); }
__host__ __device__ constexpr uint64_t dconst(uint32_t lbo, uint32_t sbo, uint32_t swz) {
    return ((uint64_t)(lbo >> 4) << 16) | ((uint64_t)(sbo >> 4) << 32) | ((uint64_t)swz << 62);
}
__device__ __forceinline__ uint32_t mkdesc(uint32_t addr, uint64_t c) { return (uint32_t)c | ((addr & 0x3FFFF) >> 4); }
#define WG_FENCE() asm volatile("wgmma.fence.sync.aligned;" ::: "memory")
#define WG_COMMIT() asm volatile("wgmma.commit_group.sync.aligned;" ::: "memory")
#define WG_WAIT(n) asm volatile("wgmma.wait_group.sync.aligned %0;" ::"n"(n) : "memory")
template <int N> __device__ __forceinline__ void reg_fence(float* d) {
#pragma unroll
    for (int i = 0; i < N; i++) asm volatile("" : "+f"(d[i])::"memory");
}
template <int N> __device__ __forceinline__ void reg_def(float* d) {
#pragma unroll
    for (int i = 0; i < N; i++) asm volatile("" : "=f"(d[i]));
}
template <int N> __device__ __forceinline__ void reg_def(uint32_t* d) {
#pragma unroll
    for (int i = 0; i < N; i++) asm volatile("" : "=r"(d[i]));
}
__device__ __forceinline__ bool is_unset(uint4 v) { return min(min(v.x, v.y), min(v.z, v.w)) == 0u; }
__device__ __forceinline__ uint4 nz4(uint32_t a, uint32_t b, uint32_t c, uint32_t d) { return make_uint4(max(a, 1u), max(b, 1u), max(c, 1u), max(d, 1u)); }
__device__ __forceinline__ void wait_flags(const uint32_t* p, uint32_t target, uint32_t mask) {
    int n = 0;
    while (~__ballot_sync(~0u, ld_relaxed(p) == target) & mask) { if (++n > SPIN_LIMIT) __trap(); }
    asm volatile("fence.acquire.gpu;" ::: "memory");
}
__device__ __forceinline__ float silu_bf(uint32_t cbits) {
    const float c = __uint_as_float(cbits << 16);
    return bf_round(__fdividef(c, 1.f + fminf(ex2(-1.4426950408889634f * c), 1e30f)));
}
__device__ __forceinline__ void gemv_part(uint32_t wmbuf, int wp, int lane) {
    const uint32_t wa = wmbuf + wp * 512 + (8 * (lane >> 4) + (lane & 7)) * 32 + ((lane >> 3) & 1) * 16;
    float d[4] = {};
#pragma unroll
    for (int i = 0; i < 4; i++) {
        uint32_t A[4];
        const float2 v = lds2f(wmbuf + 28672 + (wp + 8 * i) * 32 + (lane & 3) * 8);
        ldsm4t(wa + (i < 3 || wp < 4 ? i : 0) * 4096, A);
        mma16816(d, A[0], A[1], A[2], A[3], __float_as_uint(v.x), __float_as_uint(v.y));
    }
    if ((lane & 3) == 0) {
        sts1(wmbuf + 29696 + (wp * 16 + (lane >> 2)) * 4, __float_as_uint(d[0]));
        sts1(wmbuf + 29696 + (wp * 16 + 8 + (lane >> 2)) * 4, __float_as_uint(d[2]));
    }
}
__device__ __forceinline__ uint32_t mod_word(float v, int col, uint32_t target) {
    v = bf_round(v);
    if ((col >= DM && col < 2 * DM) || (col >= 4 * DM && col < 5 * DM)) v += 1.f;
    return (pack2(v, 0.f) << 16) | (target & 0xFFFFu);
}
__device__ __forceinline__ const uint4* mod_src(int i, int r, int j, bool p2) {
    i = min(i, p2 ? 251 : 223);
    return (const uint4*)g_mod + (r & 7) * (6 * DM / 4) + (i < 224 ? (p2 ? 336 : 0) + i : (i < 238 ? 14 * j + i : 14 * j + i + 322));
}
__device__ __forceinline__ void mod_store(uint32_t sb, uint4 v, const uint4* src, int i) {
    const uint32_t tag = lds1(sb + M_EPOCH) + 1;
    while (__any_sync(~0u, (((v.x ^ tag) | (v.y ^ tag) | (v.z ^ tag) | (v.w ^ tag)) & 0xFFFFu) != 0u)) v = ld_relaxed4(src);
    if (i < 224) {
        const int isc = i >= 112, c4 = i - 112 * isc;
        const uint32_t a = sb + M_ST + (c4 >> 2) * 64 + (c4 & 1) * 32 + (c4 & 2) * 4 + (isc ? 0 : 4);
        sts1(a, __byte_perm(v.x, v.y, 0x7632));
        sts1(a + 16, __byte_perm(v.z, v.w, 0x7632));
    } else if (i < 252) {
        sts4(sb + M_G + (i - 224) * 16, make_uint4(v.x & 0xFFFF0000u, v.y & 0xFFFF0000u, v.z & 0xFFFF0000u, v.w & 0xFFFF0000u));
    }
}
__device__ __forceinline__ int pass_f(int fs, int ps) { return 224 * fs + ((fs & 1) ? (ps == 0 ? 96 : ps == 1 ? 32 : 0) : (ps == 0 ? 0 : ps == 1 ? 128 : 192)); }
__device__ __forceinline__ constexpr uint32_t slot_off(int l) { return l * 16384; }
__device__ __forceinline__ constexpr int g1_slot(int s) { return s % 7; }
__device__ __noinline__ void x1_fix(const uint32_t* g, uint32_t sa, int s) {
#pragma unroll 1
    for (int k = 4 * s; k < 4 * s + 4;) {
        const uint4 v = ld_relaxed4((const uint4*)(g + k * 256));
        sts4(sa + k * 1024, v);
        k += 2 * __all_sync(~0u, min(min(v.x, v.y), min(v.z, v.w)) != 0u);
    }
    __syncwarp();
}
struct LnRow { uint32_t nm, hi, lo; };
__device__ __forceinline__ LnRow ln_coeffs(float mean, float msq) {
    const float var = bf_round(fmaxf(msq - mean * mean, 0.f));
    float sd;
    asm("sqrt.approx.f32 %0, %1;" : "=f"(sd) : "f"(bf_round(var + 1e-5f)));
    const float inv = rcp(bf_round(sd)), hi = bf_round(inv);
    LnRow c;
    c.nm = pack2(-bf_round(mean) * hi, -bf_round(mean) * hi);
    c.hi = pack2(hi, hi);
    c.lo = pack2(inv - hi, inv - hi);
    return c;
}
__device__ __forceinline__ uint32_t hadd2(uint32_t a, uint32_t b) { uint32_t r; asm("add.rn.bf16x2 %0, %1, %2;" : "=r"(r) : "r"(a), "r"(b)); return r; }
__device__ __forceinline__ uint32_t ln_norm(uint32_t x, const LnRow& c) {
    return hfma2(x, c.hi, c.nm);
}
__device__ __forceinline__ uint32_t ln_mod(uint32_t y, uint32_t sc, uint32_t sh) {
    return hfma2(y, sc, sh);
}

#define LOADW bulk_e(dst, g_wd + (size_t)((f >> 5) * 4 + nq) * 1792, 7168, bar);
template <int sec> __device__ __forceinline__ void ring_loader(const Params& p, uint32_t sb_, int r_, int j_, int lane) {
    const uint32_t sb = opaque(sb_);
    const int r = opaque(r_), j = opaque(j_), nq = j >> 1, fs = 4 * (j & 1) + nq;
    const int fa = pass_f(fs, 0), fb = pass_f(fs, 1), fc = pass_f(fs, 2);
    const uint32_t* h2src = (const uint32_t*)__shfl_sync(~0u, (unsigned long long)(p.actb + (size_t)r * RB_WORDS + RB_H2), 0);
    const CUtensorMap* gmap = (const CUtensorMap*)__shfl_sync(~0u, (unsigned long long)(&p.ga + sec), 0);
#define BAR(i) (sb + M_BAR + 8 * (i))
#define kh (j & 1)
            int sl = 0;
#pragma unroll 1
            for (int s = 0; s < 28; s++) {
                if (s == 7) { wait_flags(g_flag + (8 * r + j) * 128 + 96 + lane, lds1(sb + M_EPOCH) + 1, 0xFFFFu); fence_async_global(); }
                const int ps = s < 14 ? 0 : s < 21 ? 1 : 2;
                const uint32_t half = ps < 2 ? 8192 : 4096;
                const int sp = sl;
                if (s >= PACE && s < PACE_END) mbar_wait(BAR(B_FULL + s - PACE), 0);
                mbar_wait(BAR(B_EMPTY + sp), (s >= 7 && s < 14) || s >= 21);
                expect_e(BAR(B_FULL + sp), half);
                tma3_e(sb + slot_off(sp) + sec * half, gmap + 2 * ps, 0, ps ? 64 * sl : 32 * s, ps == 0 ? fa >> 6 : ps == 1 ? fb >> 6 : fc >> 5, BAR(B_FULL + sp));
                sl = sl == 6 ? 0 : sl + 1;
            }
            if (!sec) PROFH(3);
            int e = 0;
#pragma unroll 1
            for (int grp = 0; grp < 12; grp++) {
                const int ps = grp >> 2, sidx = grp & 3;
                const bool own = sidx == nq;
                if (sec && sidx == (nq == 0)) { mbar_wait(BAR(B_HRDY + ps), 0); fence_async_global(); }
                int f = pass_f(4 * kh + sidx, ps);
#pragma unroll 1
                for (int k = 4 >> ps; k > 0; k--, e++, f += 32) {
                    const uint32_t dst = sb + slot_off(sl), bar = BAR(B_FULL + sl);
                    mbar_wait(BAR(B_EMPTY + sl), e >= 12 && e < 24);
                    if (e >= WIN) mbar_wait(BAR(B_FULL + (sl >= WIN ? sl - WIN : sl + 12 - WIN)), e - WIN >= 12);
                    expect_e(bar, sec ? (own ? 0 : 8192) : 7168);
                    if (!sec) { LOADW }
                    else if (!own) bulk_e(dst + 8192, h2src + f * 64, 8192, bar);
                    sl = sl == 11 ? 0 : sl + 1;
                }
            }
            if (!sec) PROFH(4);
}

#define PROF_PARAMS
#define PROF_ARGS
__device__ __noinline__ void helper_late(const Params& p, int r_, int j_, int warp_ PROF_PARAMS) {
    extern __shared__ __align__(1024) unsigned char smem[];
    const uint32_t sb = (uint32_t)__cvta_generic_to_shared(smem);
    const int r = opaque(r_), j = opaque(j_), warp = opaque(warp_), nq = j >> 1, b = 8 * r + j;
    uint32_t* const act = (uint32_t*)__shfl_sync(~0u, (unsigned long long)(p.actb + (size_t)r * RB_WORDS), 0);
    {
        const int lane = fresh_tid() & 31;
        const uint32_t target = lds1(sb + M_EPOCH) + 1;
        if (warp == 8) { expect_e(BAR(B_XCH), 14336); expect_e(BAR(B_XCH + 1), 14336); }
            if (warp == 9) {
#pragma unroll 1
                for (int kv = 0; kv < 2; kv++) {
                    mbar_wait(BAR(B_PUB + kv), 0);
                    wait_flags(g_flag + b * 128 + lane, target, (r >= 2 ? 6u : r == 1 ? 2u : 0u) << (8 * kv));
                    fence_async_global();
                    const uint32_t dst = sb + OFF_Y + (kv ? Y_VR : Y_K);
                    expect_e(BAR(B_KRFULL + kv), r >= 2 ? 28672 : r == 1 ? 14336 : 0);
                    if (r >= 2) bulk_e(dst, act - 2 * RB_WORDS + RB_KV + j * 7168 + kv * 3584, 14336, BAR(B_KRFULL + kv));
                    if (r >= 1) bulk_e(dst + 14336, act - RB_WORDS + RB_KV + j * 7168 + kv * 3584, 14336, BAR(B_KRFULL + kv));
                    if (kv == 0) { PROFH(8); }
                }
            } else if (warp == 8) {
                uint4 v[8];
                mbar_wait(BAR(B_WOFULL), 0);
#pragma unroll
                for (int k = 0; k < 8; k++) v[k] = ld_relaxed4(mod_src(lane + 32 * k, r, j, true));
#pragma unroll
                for (int k = 0; k < 8; k++) mod_store(sb, v[k], mod_src(lane + 32 * k, r, j, true), lane + 32 * k);
                warp_arrive(BAR(B_MOD1));
            } else if (warp == 11) {
                if (kh == 1 && r < 14) {
                    const uint32_t wmbuf = sb + OFF_X + HALF;
                    const int mcol = 2 * DM + 32 * (4 * r + nq);
                    mbar_wait(BAR(B_XFREE), 0);
                    tma3_e(wmbuf, &p.wm2, mcol, 0, 0, BAR(B_WMFULL));
                    tma3_e(wmbuf + 14336, &p.wm2, mcol, 224, 0, BAR(B_WMFULL));
#pragma unroll 1
                    for (int wd = lane; wd < 224; wd += 32) {
                        const uint32_t cb = __ldg((const uint32_t*)p.c + wd);
                        sts1(wmbuf + 28672 + (wd >> 3) * 32 + (wd & 3) * 8 + (wd & 4), pack2(silu_bf(cb & 0xFFFFu), silu_bf(cb >> 16)));
                    }
                    __syncwarp();
                    mbar_wait(BAR(B_WMFULL), 0);
                    const uint32_t wa = wmbuf + (8 * (lane >> 4) + (lane & 7)) * 64 + ((lane >> 3) & 1) * 16;
                    float d[2][4] = {};
#pragma unroll 4
                    for (int ks = 0; ks < 28; ks++) {
                        uint32_t A[8];
                        ldsm4t(wa + ks * 1024, A); ldsm4t(wa + ks * 1024 + 32, A + 4);
                        const float2 v = lds2f(wmbuf + 28672 + ks * 32 + (lane & 3) * 8);
                        mma16816(d[0], A[0], A[1], A[2], A[3], __float_as_uint(v.x), __float_as_uint(v.y));
                        mma16816(d[1], A[4], A[5], A[6], A[7], __float_as_uint(v.x), __float_as_uint(v.y));
                    }
                    const int q = lane & 3, col = mcol + 8 * q + (lane >> 2);
                    const uint32_t word = mod_word(q == 0 ? d[0][0] : q == 1 ? d[0][2] : q == 2 ? d[1][0] : d[1][2], col, target);
#pragma unroll
                    for (int i = 0; i < 8; i++) st_relaxed(g_mod + i * 6 * DM + col, word);
                }
                warp_arrive(BAR(B_WMFREE));
                mbar_wait(BAR(B_VRFULL), 0);
                l2_prefetch_e((const char*)p.wg + (size_t)b * 12544, 12544);
                l2_prefetch_e((const char*)p.wu + (size_t)b * 12544, 12544);
#pragma unroll 1
                for (int k = 0; k < (r < 12 ? 2 : 1); k++) {
                    const int u = 28 * kh + r + 16 * k;
                    expect_e(BAR(B_XFULL + k), 7168);
                    tma3_e(sb + OFF_Y + 102400, &p.dn, 0, 32 * u, 7 * j, BAR(B_XFULL + k));
                    tma3_e(sb + OFF_Y + 102400 + 3584, &p.dn, 0, 32 * u, 7 * (j ^ 1), BAR(B_XFULL + k));
                    mbar_wait(BAR(B_XFULL + k), 1);
                    asm volatile("{\n.reg .pred p;\nelect.sync _|p, 0xffffffff;\n@p cp.async.bulk.global.shared::cta.bulk_group [%0], [%1], 7168;\n"
                                 "cp.async.bulk.commit_group;\ncp.async.bulk.wait_group 0;\n}" ::"l"(g_wd + (size_t)(u * 4 + nq) * 1792), "r"(sb + OFF_Y + 102400) : "memory");
                    __syncwarp();
                }
                warp_arrive(BAR(B_FULLK));
                fence_gpu();
                if (lane < 16) st_relaxed(g_flag + (8 * lane + j) * 128 + 96 + r, target);
            }
        if (warp == 8 || warp == 11) {
            const int sec = warp == 11;
            if (sec) ring_loader<1>(p, sb, r, j, lane); else ring_loader<0>(p, sb, r, j, lane);
            mbar_wait(BAR(B_DONE), 0);
        } else if (warp == 9) {
#pragma unroll
            for (int ev = 0; ev < 4; ev++) { expect_e(BAR(B_GFULL + ev), ev < 2 ? HALF / 2 : 16384); expect_e(BAR(B_XFULL + 2 + ev), ev < 2 ? HALF / 2 : HALF - 16384); }
            mbar_wait(BAR(B_PUB + 2), 0);
            expect_e(BAR(B_FULLV), 4096); expect_e(BAR(B_FULLQ), 4096);
            const uint32_t* fp = g_flag + b * 128 + 32 + lane;
            const int par = (target - 1) & 1;
#pragma unroll 1
            for (int n = 0, ev = 0; ev < 4; n++) {
                if (ev == 1) mbar_wait(BAR(B_PUB + 3), 0);
                uint32_t ok = __ballot_sync(~0u, ld_relaxed(fp) == target) >> (8 * ev);
                while ((ok & 0xFFu) == 0xFFu) {
                    if (ev == 1) mbar_wait(BAR(B_FULLK), 1);
                    asm volatile("fence.acquire.gpu;" ::: "memory");
                    fence_async_global();
                    const int tile = (ev & 1) + (ev >> 1) * par * 2;
                    const uint32_t dst = sb + (ev == 0 ? OFF_X : OFF_Y + (ev & 1) * HALF), first = ev < 2 ? HALF / 2 : 16384;
                    const char* src = (const char*)(act + RB_O + ((ev >> 1) * 2 + tile) * 14336);
                    if (ev >= 2) bulk_e(sb + OFF_X + X_STAT + (ev & 1) * 49152, act + RB_ST + tile * 1024, 4096, BAR(B_FULLV + (ev & 1)));
                    bulk_e(dst, src, first, BAR(B_GFULL + ev));
                    bulk_e(dst + first, src + first, HALF - first, BAR(B_XFULL + 2 + ev));
                    if (ev) PROFH(4 + ev);
                    ev++; ok >>= 8;
                }
                if (n > SPIN_LIMIT) __trap();
            }
            mbar_wait(BAR(B_XFULL + 5), 1);
#pragma unroll 1
            for (int hf = 0; hf < 2; hf++) {
                const int tile = (par ^ 1) * 2 + hf;
                uint4* xz = (uint4*)(act + RB_X1 + tile * 14336 + j * 1792) + lane;
#pragma unroll
                for (int i = 0; i < 14; i++) xz[i * 32] = make_uint4(0, 0, 0, 0);
                ((uint4*)(act + RB_ST + (tile * 8 + j) * 128))[lane] = make_uint4(0, 0, 0, 0);
            }
#pragma unroll 1
            for (int ps = 0; ps < 3; ps++) {
                mbar_wait(BAR(B_PUB + 6 + ps), 0);
                wait_flags(g_flag + b * 128 + 64 + lane, target, (0x55u << kh) << (8 * ps));
                warp_arrive(BAR(B_HRDY + ps));
                PROFH(9 + ps);
            }
        } else {
#pragma unroll 1
            for (int k = 0; k < 9; k++) {
                uint32_t* fp = k < 2 ? g_flag + (b + 8 * lane) * 128 + k * 8 + lane : g_flag + (8 * r + lane) * 128 + 16 + k * 8 + j;
                mbar_wait(BAR(B_PUB + k), 0);
                if (k != 4 && k != 5) fence_gpu();
                if (k < 2 ? (lane == 1 || lane == 2) : lane < 8) st_relaxed(fp, target);
                if (k >= 3 && k <= 5) PROFH(k - 3);
            }
        }
    }
}

__global__ void __cluster_dims__(2, 1, 1) __launch_bounds__(384, 1) fused_block_kernel(const __grid_constant__ Params p) {
    extern __shared__ __align__(1024) unsigned char smem[];
    const uint32_t sb = (uint32_t)__cvta_generic_to_shared(smem);
    const int tid = threadIdx.x, lane = tid & 31, warp = __shfl_sync(~0u, tid >> 5, 0);
    const int m = blockIdx.x >> 1;
    int r, nq;
    if (m < 4) { r = 15; nq = m; }
    else if (m < 36) { r = (m - 4) & 7; nq = (m - 4) >> 3; }
    else { nq = (m - 36) / 7; r = m - 28 - 7 * nq; }
    const int j = opaque(2 * nq + (blockIdx.x & 1)), b = 8 * r + j, fs = 4 * kh + nq;
#define act (p.actb + (size_t)r * RB_WORDS)
    constexpr uint32_t sc = 0;
    if (lane == 0 && warp < 9 && warp != 6 && warp != 7) {
        const int i0 = warp == 8 ? 0 : 8 + 8 * warp, cnt = warp == 0 || warp == 8 ? 1 : warp < 3 ? 2 : 8;
#pragma unroll
        for (int k = 0; k < 8; k++) if (i0 + k != B_WMFULL) mbar_init(BAR(i0 + k), cnt);
        if (warp == 8) mbar_init(BAR(B_WMFULL), 1);
        asm volatile("fence.mbarrier_init.release.cluster;" ::: "memory");
        fence_async_smem();
    }

    if (warp >= 8) {
        const int lane = fresh_tid() & 31;
        const bool early = kh == 0, gemv = r < 14;
        const int mcol = early ? 16 * (4 * r + nq) : 2 * DM + 32 * (4 * r + nq);
        const uint32_t wmbuf = sb + OFF_Y + HALF;
        if (warp == 8) {
            __syncwarp();
            expect_e(BAR(B_WMFULL), gemv ? 28672 >> early : 0);
            if (early && gemv) { tma3_e(wmbuf, &p.wm, mcol, 0, 0, BAR(B_WMFULL)); tma3_e(wmbuf + 7168, &p.wm, mcol, 224, 0, BAR(B_WMFULL)); }
#pragma unroll
            for (int kb = 0; kb < XFIRST; kb++) {
                expect_e(BAR(B_XFULL + kb), 16384);
                tma3_e(sb + OFF_X + kb * 16384, &p.xm, 64 * kb, 128 * r, 0, BAR(B_XFULL + kb));
            }
        }
        asm volatile("setmaxnreg.dec.sync.aligned.u32 56;");
        if (warp == 9) {
#pragma unroll
            for (int i = 56; i < 64; i++) init_e(BAR(i), 1);
            fence_async_smem();
        }
        bar_arrive(0, 384);
        asm volatile("barrier.cluster.arrive.relaxed.aligned;" ::: "memory");
        if (warp == 8) {
#pragma unroll
            for (int kb = XFIRST; kb < 7; kb++) {
                expect_e(BAR(B_XFULL + kb), 16384);
                tma3_e(sb + OFF_X + kb * 16384, &p.xm, 64 * kb, 128 * r, 0, BAR(B_XFULL + kb));
            }
            if (KDELAY >= 0) { mbar_wait(BAR(B_XFULL + KDELAY), 0); l2_prefetch_e((const char*)p.wqkv + (size_t)b * 9408, 9408); }
#pragma unroll 1
            for (int mt = 0; mt < 4; mt++) {
                if (mt == 1) bar_sync(9, 384);
                if (mt == 3) mbar_wait(BAR(B_WMFREE), 0);
                if (mt == 1 && early) mbar_wait(BAR(B_WMFREE), 0);
                if (mt) mbar_wait(BAR(mt == 1 ? (VGATE == 1 ? B_XFREE : B_FULLK) : mt == 2 ? B_MOD1 : B_VRFULL), 0);
                const uint32_t bar = BAR(mt == 3 ? B_WOFULL : B_FULLK + mt), dst = sb + (mt < 2 ? OFF_Y : OFF_X) + (mt & 1) * HALF;
                const int c0 = (mt < 2 ? DM + DM * mt : 0) + 56 * j - 8 * kh;
                if (!sc) {
                    expect_e(bar, HALF);
                    tma3_e(dst, mt == 3 ? &p.wo : &p.qkv, c0, 0, 0, bar);
                    tma3_e(dst + HALF / 2, mt == 3 ? &p.wo : &p.qkv, c0, 224, 0, bar);
                }
            }
        } else {
            if (KDELAY < 0 && warp == 10) l2_prefetch_e((const char*)p.wqkv + (size_t)b * 9408, 9408);
            bar_sync(9, 384);
            if (sc) return;
            if (warp == 11 && early) {
                const uint32_t target = lds1(sb + M_EPOCH) + 1;
                mbar_wait(BAR(B_GEMV), 0);
                float sum = 0.f;
#pragma unroll
                for (int i = 0; i < 8; i++) sum += *(const float*)(smem + OFF_Y + HALF + 29696 + (i * 16 + (lane & 15)) * 4);
                uint32_t* mg = g_mod + mcol + (lane & 15) + (lane >> 4) * 4 * 6 * DM;
                const uint32_t word = mod_word(sum, mcol, target);
                if (gemv) { st_relaxed(mg, word); st_relaxed(mg + 6 * DM, word); st_relaxed(mg + 12 * DM, word); st_relaxed(mg + 18 * DM, word); }
            }
        }
    }
    if (LIKELY(warp < 8)) {
        const int w = (warp >> 2) ^ WSWAP, wi = warp & 3;
#define COORDS const int t = fresh_tid() & 127, lane = t & 31, q = lane & 3, lr = lane >> 2, ra = 64 * w + 16 * wi + lr; \
        const uint32_t lx = (lane >> 4) ^ (lane & 7), mrow = (64 * w + 16 * wi + ((lane >> 3) & 1) * 8 + (lane & 7)) * 128; \
        (void)q; (void)lr; (void)ra; (void)lx; (void)mrow;
        const int sid = 2 * (j & 3) + w;
#define RUN(k) (!sc || sid == (k))
#define WAIT(i, par) mbar_wait_c(BAR(i), (par) | sc)
        constexpr uint64_t DB128 = dconst(4096, 1024, 1);
        {
            const int wd = fresh_tid();
            const uint32_t cb = wd < 224 ? __ldg((const uint32_t*)p.c + wd) : 0u;
            if (wd == 255 && !sc) sts1(sb + M_EPOCH, atomicAdd(&g_ticket, 1u) / NCTA);
            sts1(sb + OFF_Y + HALF + 28672 + (wd >> 3) * 32 + (wd & 3) * 8 + (wd & 4), pack2(silu_bf(cb & 0xFFFFu), silu_bf(cb >> 16)));
        }
        bar_arrive(9, 384);
        bar_sync(0, 384);
        asm volatile("barrier.cluster.arrive.relaxed.aligned;" ::: "memory");
        asm volatile("setmaxnreg.inc.sync.aligned.u32 224;");
        PROFC(0);
        uint32_t xr[16];
        {
            COORDS
            uint32_t h[112];
            LnRow ca, cb;
            const int mi = min(128 * w + t, 223);
            const uint4* msrc = mod_src(mi, r, j, false);
            uint4 mv;
            {
                float ds[4] = {}, da[2][4] = {}, db[2][4] = {};
                const uint32_t ONE2 = 0x3F803F80u;
#pragma unroll
                for (int kb = 0; kb < 7; kb++) {
                    if (kb == GEMV_AT && kh == 0) { WAIT(B_WMFULL, 0); gemv_part(sb + OFF_Y + HALF, warp, lane); warp_arrive(BAR(B_GEMV)); }
                    WAIT(B_XFULL + kb, 0);
#pragma unroll
                    for (int k4 = 0; k4 < 4; k4++) ldsm4(sb + OFF_X + mrow + kb * 16384 + (((2 * k4) ^ lx) << 4), h + 16 * kb + 4 * k4);
#pragma unroll
                    for (int k4 = 0; k4 < 4; k4++) {
                        const uint32_t* f = h + 16 * kb + 4 * k4;
                        mma16816(ds, f[0], f[1], f[2], f[3], ONE2, ONE2);
                        mma1688(da[0], f[0], f[1], f[0]); mma1688(db[0], f[0], f[1], f[1]);
                        mma1688(da[1], f[2], f[3], f[2]); mma1688(db[1], f[2], f[3], f[3]);
                    }
                }
#pragma unroll
                for (int i = 0; i < 4; i++) {
                    const int ch = 7 * j + 2 * i + (lane >> 4);
                    ldsm4(sb + OFF_X + mrow + (ch >> 3) * 16384 + (((ch ^ lane) & 7) << 4), xr + 4 * i);
                }
                mv = ld_relaxed4(msrc);
                warp_arrive(BAR(B_XFREE));
                float qa = (lr & 1) ? da[0][1] + da[1][1] : da[0][0] + da[1][0];
                float qb = (lr & 1) ? db[0][3] + db[1][3] : db[0][2] + db[1][2];
                const int src = (lane & ~3) | (lr >> 1);
                qa = __shfl_sync(~0u, qa, src);
                qb = __shfl_sync(~0u, qb, src);
                ca = ln_coeffs(ds[0] * (1.f / DM), qa * (1.f / DM));
                cb = ln_coeffs(ds[2] * (1.f / DM), qb * (1.f / DM));
#pragma unroll
                for (int i = 0; i < 4 * NPRE; i += 2) { h[i] = ln_norm(h[i], ca); h[i + 1] = ln_norm(h[i + 1], cb); }
            }
            PROFC(1);
            {
                float ak[28], av[28], aq[28];
                uint32_t kp[14], vp[14];
                const uint64_t bq0 = (DB128 & ~0xFFFFFFFFull) | (mkdesc(sb + OFF_X, DB128) + kh), bk0 = bq0 + (OFF_Y >> 4), bv0 = bk0 + (HALF >> 4);
                uint32_t* kvg = act + RB_KV + j * 7168 + (8 * w + 2 * wi) * 224 + lane;
                mod_store(sb, mv, msrc, mi);
                bar_sync(3, 256);
                if (warp == 0) warp_arrive(BAR(B_MOD1));
                WAIT(B_FULLK, 0);
                PROFC(2);
                reg_def<28>(ak);
#pragma unroll
                for (int g4 = 0; g4 < 4; g4++) {
#pragma unroll
                    for (int ks = 7 * g4; ks < 7 * g4 + 7; ks++) {
                        const uint4 st = *(const uint4*)(smem + M_ST + ks * 64 + q * 16);
                        if (ks >= NPRE) {
                            h[4 * ks] = ln_norm(h[4 * ks], ca); h[4 * ks + 1] = ln_norm(h[4 * ks + 1], cb);
                            h[4 * ks + 2] = ln_norm(h[4 * ks + 2], ca); h[4 * ks + 3] = ln_norm(h[4 * ks + 3], cb);
                        }
                        h[4 * ks] = ln_mod(h[4 * ks], st.x, st.y); h[4 * ks + 1] = ln_mod(h[4 * ks + 1], st.x, st.y);
                        h[4 * ks + 2] = ln_mod(h[4 * ks + 2], st.z, st.w); h[4 * ks + 3] = ln_mod(h[4 * ks + 3], st.z, st.w);
                    }
                    WG_FENCE();
#pragma unroll
                    for (int ks = 7 * g4; ks < 7 * g4 + 7; ks++) wgmma_rl_56(ak, h[4 * ks], h[4 * ks + 1], h[4 * ks + 2], h[4 * ks + 3], bk0 + ks * 128, ks != 0);
                }
                WG_COMMIT();
                PROFC(3);
                reg_def<28>(av);
                WG_WAIT(0);
                reg_fence<28>(ak);
#pragma unroll
                for (int g = 0; g < 7; g++) {
                    kp[2 * g] = pack2(ak[4 * g], ak[4 * g + 1]); kp[2 * g + 1] = pack2(ak[4 * g + 2], ak[4 * g + 3]);
                    kvg[g * 32] = kp[2 * g]; kvg[224 + g * 32] = kp[2 * g + 1];
                }
                warp_arrive(BAR(B_PUB));
                PROFC(4);
                if (KEARLY) WAIT(B_FULLV, 0);
                WG_FENCE();
#pragma unroll
                for (int ks = KEARLY ? 0 : 8; ks < 28; ks++) wgmma_rl_56(av, h[4 * ks], h[4 * ks + 1], h[4 * ks + 2], h[4 * ks + 3], bv0 + ks * 128, ks != 0);
                WG_COMMIT();
                reg_def<28>(aq);
                WAIT(B_FULLQ, 0);
                WG_FENCE();
#pragma unroll
                for (int ks = 0; ks < VPRE; ks++) wgmma_rl_56(aq, h[4 * ks], h[4 * ks + 1], h[4 * ks + 2], h[4 * ks + 3], bq0 + ks * 128, ks != 0);
                WG_COMMIT();
                WG_WAIT(1);
                reg_fence<28>(av);
#pragma unroll
                for (int g = 0; g < 7; g++) {
                    vp[2 * g] = pack2(av[4 * g], av[4 * g + 1]); vp[2 * g + 1] = pack2(av[4 * g + 2], av[4 * g + 3]);
                    kvg[3584 + g * 32] = vp[2 * g]; kvg[3584 + 224 + g * 32] = vp[2 * g + 1];
                }
                warp_arrive(BAR(B_PUB + 1));
                PROFC(5);
                if (!VPRE) WAIT(B_FULLQ, 0);
                WG_FENCE();
#pragma unroll
                for (int ks = VPRE; ks < 28; ks++) wgmma_rl_56(aq, h[4 * ks], h[4 * ks + 1], h[4 * ks + 2], h[4 * ks + 3], bq0 + ks * 128, ks != 0);
                WG_COMMIT();
                WAIT(B_PUB + 1, 0);
                const uint32_t rg = 8 * w + 2 * wi + ((lane >> 3) & 1);
                const uint32_t ko = sb + OFF_Y + Y_KOWN + rg * 896 + (lane & 7) * 16, qo = sb + OFF_Y + Y_Q + rg * 1024 + (lane >> 4) * 128 + (lane & 7) * 16;
#pragma unroll
                for (int g = 0; g < 6; g += 2) {
                    stsm4(ko + (g + (lane >> 4)) * 128, kp[2 * g], kp[2 * g + 1], kp[2 * g + 2], kp[2 * g + 3]);
                    stsm4(ko + (Y_VOWN - Y_KOWN) + (g + (lane >> 4)) * 128, vp[2 * g], vp[2 * g + 1], vp[2 * g + 2], vp[2 * g + 3]);
                }
                stsm4(ko + (lane >> 4) * (Y_VOWN - Y_KOWN) + 6 * 128, kp[12], kp[13], vp[12], vp[13]);
                WG_WAIT(0);
                reg_fence<28>(aq);
                __syncwarp();
                if (lane < 3 && w == 1) mbar_arrive(BAR(B_EMPTY + lane));
                uint32_t qp[14];
#pragma unroll
                for (int i = 0; i < 14; i++) qp[i] = pack2(aq[2 * i], aq[2 * i + 1]);
                stsm4(qo, qp[0], qp[1], qp[2], qp[3]);
                stsm4(qo + 256, qp[4], qp[5], q < 2 ? qp[6] : 0u, q < 2 ? qp[7] : 0u);
                stsm4(qo + 512, q < 2 ? 0u : qp[6], q < 2 ? 0u : qp[7], qp[8], qp[9]);
                stsm4(qo + 768, qp[10], qp[11], qp[12], qp[13]);
                fence_async_smem();
                if (w == 0) { bar_arrive(4, 256); bar_sync(1, 128); } else { bar_arrive(5, 256); bar_sync(4, 256); }
            }
        }
        PROFC(6);
        WAIT(B_KRFULL, 0);
        if (ATT_OFF && w == ATT_WG) { const uint32_t t0 = clock(); while (clock() - t0 < ATT_OFF) {} }
        PROFC(7);
        if (RUN(2)) {
#pragma unroll 1
            for (int hf = sc; hf < 2; hf++) {
                COORDS
                if (ASYM && hf > w) bar_sync(5, 256);
                float s[160];
                const float CS = 0.18898223650461361f * 1.4426950408889634f;
                const float NEG = __int_as_float(0xFF800000);
                constexpr uint64_t DQ = dconst(128, 1024, 0), DK = dconst(128, 896, 0);
                {
                    const uint32_t qd = mkdesc(sb + OFF_Y + Y_Q + hf * 8192 + w * 512, DQ), kd = mkdesc(sb + OFF_Y + Y_K + hf * 8 * 896 + w * 384, DK);
                    reg_def<160>(s);
                    WG_FENCE();
                    wgmma_sk_160<DQ, DK>(s, qd, kd, 0);
                    wgmma_sk_160<DQ, DK>(s, qd + 16, kd + 16, 1);
                    wgmma_sk_160<DQ, DK>(s + 80, qd, kd + 20 * 56, 0);
                    wgmma_sk_160<DQ, DK>(s + 80, qd + 16, kd + 20 * 56 + 16, 1);
                    WG_COMMIT();
                    WG_WAIT(0);
                    reg_fence<160>(s);
                }
                if (r < 2) {
                    const int pmin = 4 - 2 * r - hf;
#pragma unroll
                    for (int p4 = 0; p4 < 4; p4++)
                        if (p4 < pmin) {
#pragma unroll
                            for (int i = 0; i < 32; i++) asm volatile("mov.b32 %0, 0xFF800000;" : "=f"(s[32 * p4 + i]));
                        }
                }
                const bool c0 = 2 * q > lr, c1 = 2 * q + 1 > lr;
#pragma unroll
                for (int pp = 0; pp < 4; pp++) {
                    const bool me = pp == wi;
                    float* e = s + 8 * pp;
                    if (me && !c0) { e[0] = NEG; e[6] = NEG; }
                    if (me && !c1) { e[1] = NEG; e[7] = NEG; }
                    if (me) { e[2] = NEG; e[3] = NEG; }
                    e = s + 8 * (pp + 16);
                    if (me && c0) { e[0] = NEG; e[6] = NEG; }
                    if (me && c1) { e[1] = NEG; e[7] = NEG; }
                    if (me) { e[4] = NEG; e[5] = NEG; }
                }
#pragma unroll
                for (int i = 0; i < 24; i++) s[i] = (i >> 3) < wi ? s[136 + i] : s[i];
                int i0 = 0x80000000, i1 = 0x80000000, i2 = 0x80000000, i3 = 0x80000000;
#pragma unroll
                for (int pp = 0; pp < 17; pp++) {
                    const float* e = s + 8 * pp;
                    i0 = __vimax3_s32(i0, __float_as_int(e[0]), __float_as_int(e[1])); i1 = __vimax3_s32(i1, __float_as_int(e[2]), __float_as_int(e[3]));
                    i2 = __vimax3_s32(i2, __float_as_int(e[4]), __float_as_int(e[5])); i3 = __vimax3_s32(i3, __float_as_int(e[6]), __float_as_int(e[7]));
                }
                i0 = max(i0, i2); i1 = max(i1, i3);
                i0 = max(i0, __shfl_xor_sync(~0u, i0, 1)); i1 = max(i1, __shfl_xor_sync(~0u, i1, 1));
                i0 = max(i0, __shfl_xor_sync(~0u, i0, 2)); i1 = max(i1, __shfl_xor_sync(~0u, i1, 2));
                if (__any_sync(~0u, (i0 | i1) < 0)) {
                    uint32_t u0 = ~0u, u1 = ~0u, u2 = ~0u, u3 = ~0u;
#pragma unroll
                    for (int pp = 0; pp < 17; pp++) {
                        const float* e = s + 8 * pp;
                        u0 = __vimin3_u32(u0, __float_as_uint(e[0]), __float_as_uint(e[1])); u1 = __vimin3_u32(u1, __float_as_uint(e[2]), __float_as_uint(e[3]));
                        u2 = __vimin3_u32(u2, __float_as_uint(e[4]), __float_as_uint(e[5])); u3 = __vimin3_u32(u3, __float_as_uint(e[6]), __float_as_uint(e[7]));
                    }
                    u0 = min(u0, u2); u1 = min(u1, u3);
                    u0 = min(u0, __shfl_xor_sync(~0u, u0, 1)); u1 = min(u1, __shfl_xor_sync(~0u, u1, 1));
                    u0 = min(u0, __shfl_xor_sync(~0u, u0, 2)); u1 = min(u1, __shfl_xor_sync(~0u, u1, 2));
                    if (i0 < 0) i0 = u0;
                    if (i1 < 0) i1 = u1;
                }
                const float ma = __int_as_float(i0), mb = __int_as_float(i1);
                const float na = -ma * CS, nb = -mb * CS;
                PROFC(8 + 3 * hf);
                {
                    WAIT(B_VRFULL, 0);
                    float o[16] = {}, rs[4] = {};
                    const uint32_t va = sb + OFF_Y + Y_VR + (8 * hf + ((lane >> 3) & 1)) * 896 + (3 * w + (lane >> 4)) * 128 + (lane & 7) * 16;
                    constexpr uint32_t OWN = Y_VOWN - 32 * 896;
#pragma unroll
                    for (int pp = 0; pp < 17; pp++) {
                        uint32_t B[8];
                        const uint32_t v = va + pp * 1792 + (pp < 3 ? (pp < wi ? 17 * 1792 + OWN : 0) : pp == 16 ? OWN : pp >= 12 ? hf * OWN : 0);
                        ldsm4t(v, B); ldsm4t(v + 256, B + 4);
                        float e[8];
#pragma unroll
                        for (int i = 0; i < 8; i++) e[i] = ex2(fmaf(s[8 * pp + i], CS, (i & 2) ? nb : na));
                        const uint32_t p0 = pack2(e[0], e[1]), p1 = pack2(e[2], e[3]), p2 = pack2(e[4], e[5]), p3 = pack2(e[6], e[7]);
                        mma16816(rs, p0, p1, p2, p3, 0x3F803F80u, 0x3F803F80u);
#pragma unroll
                        for (int g = 0; g < 4; g++) mma16816(o + 4 * g, p0, p1, p2, p3, B[2 * g], B[2 * g + 1]);
                    }
                    PROFC(9 + 3 * hf);
                    const float ia = rcp(rs[0]), ib = rcp(rs[2]);
                    uint32_t* og = act + RB_O + hf * 14336 + (7 * j + 3 * w) * 256 + wi * 64 + lane;
#pragma unroll
                    for (int g = 0; g < 4; g++) {
                        if ((g == 3 - 3 * w) ? ((q >> 1) == w) : true) {
                            og[g * 256] = pack2(o[4 * g] * ia, o[4 * g + 1] * ia);
                            og[g * 256 + 32] = pack2(o[4 * g + 2] * ib, o[4 * g + 3] * ib);
                        }
                    }
                    warp_arrive(BAR(B_PUB + 2 + hf));
                    PROFC(10 + 3 * hf);
                }
            }
        }
        uint32_t x1p[14];
        COORDS
        constexpr uint64_t DT = dconst(1024, 128, 0);
        const int tile = opaque((lds1(sb + M_EPOCH) & 1) * 2 + w);
        if (RUN(4)) {
            float ac[28];
            const uint32_t ad = mkdesc(sb + (w ? OFF_Y + HALF : OFF_X), DT), bd = mkdesc(sb + OFF_X + HALF, DB128) + kh;
            WAIT(B_WOFULL, 0);
            WAIT(B_MOD1, 1);
            WAIT(B_GFULL + w, 0);
            PROFC(28);
            reg_def<28>(ac);
#pragma unroll 1
            for (int u = 0; u < 4; u++) {
                if (u == 2) WAIT(B_XFULL + 2 + w, 1);
                WG_FENCE();
#pragma unroll
                for (int i = 0; i < 7; i++) wgmma_ss_56<DT, DB128>(ac, ad + (7 * u + i) * 128, bd + (7 * u + i) * 128, (u | i) != 0);
            }
            WG_COMMIT();
            WG_WAIT(0);
            reg_fence<28>(ac);
            PROFC(14);
            __syncwarp();
            if (lane < 3) mbar_arrive(BAR(B_EMPTY + 4 - w + lane));
            if (lane < 3 && w == 0) mbar_arrive(BAR(B_EMPTY + lane));
            float ds[4] = {}, da[4] = {}, db[4] = {};
            uint32_t* xo = act + RB_X1 + tile * 14336 + 7 * j * 256 + wi * 64 + lane;
#pragma unroll
            for (int g = 0; g < 7; g++) {
                const float2 ga = *(const float2*)(smem + M_G + (8 * g + 2 * q) * 4);
                x1p[2 * g] = pack2(fmaf(ga.x, ac[4 * g], bf_lo(xr[2 * g])), fmaf(ga.y, ac[4 * g + 1], bf_hi(xr[2 * g])));
                x1p[2 * g + 1] = pack2(fmaf(ga.x, ac[4 * g + 2], bf_lo(xr[2 * g + 1])), fmaf(ga.y, ac[4 * g + 3], bf_hi(xr[2 * g + 1])));
                st_relaxed(xo + g * 256, nz(x1p[2 * g])); st_relaxed(xo + g * 256 + 32, nz(x1p[2 * g + 1]));
                mma1688(ds, x1p[2 * g], x1p[2 * g + 1], 0x3F803F80u);
                mma1688(da, x1p[2 * g], x1p[2 * g + 1], x1p[2 * g]);
                mma1688(db, x1p[2 * g], x1p[2 * g + 1], x1p[2 * g + 1]);
            }
            const int src = (lane & ~3) | (lr >> 1);
            const float qa = __shfl_sync(~0u, (lr & 1) ? da[1] : da[0], src), qb = __shfl_sync(~0u, (lr & 1) ? db[3] : db[2], src);
            const float kk = (q & 1) ? ((q & 2) ? qb : qa) : ((q & 2) ? ds[2] : ds[0]);
            st_relaxed(act + RB_ST + ((tile * 8 + j) * 64 + 16 * wi + lr + 4 * (q & 2)) * 2 + (q & 1), nz(__float_as_uint(kk)));
            __syncwarp();
            if (lane < 2) mbar_arrive(BAR(B_PUB + 4 + w));
        } else reg_def<14>(x1p);
        PROFC(15);
        uint32_t h2a[32], h2b[24];
        {
            const int fa = pass_f(fs, 0), fb = pass_f(fs, 1), fc = pass_f(fs, 2);
            uint32_t* h2g = act + RB_H2 + (8 * w + 2 * wi) * 32 + lane;
            const uint32_t a0 = mkdesc(sb + OFF_Y + w * HALF, DT);
            if (RUN(3)) {
                LnRow ca, cb;
                {
                    const uint32_t* sg = act + RB_ST + ((tile * 8 + 2 * q) * 64 + 16 * wi + lr) * 2;
                    uint2 u[4];
                    WAIT(B_FULLV + w, 1);
                    PROFC(16);
#pragma unroll
                    for (int i = 0; i < 4; i++) { const float2 v = lds2f(sb + OFF_X + X_STAT + w * 49152 + ((2 * q + (i >> 1)) * 64 + 16 * wi + lr + 8 * (i & 1)) * 8); u[i] = make_uint2(__float_as_uint(v.x), __float_as_uint(v.y)); }
                    while (__any_sync(~0u, min(min(min(u[0].x, u[0].y), min(u[1].x, u[1].y)), min(min(u[2].x, u[2].y), min(u[3].x, u[3].y))) < 1u - sc)) {
#pragma unroll
                        for (int i = 0; i < 4; i++) u[i] = ld_relaxed2(sg + (i >> 1) * 128 + (i & 1) * 16);
                    }
                    warp_arrive(BAR(B_EMPTY + 3 + 3 * w));
                    float v[4] = {__uint_as_float(u[0].x) + __uint_as_float(u[2].x), __uint_as_float(u[0].y) + __uint_as_float(u[2].y),
                                  __uint_as_float(u[1].x) + __uint_as_float(u[3].x), __uint_as_float(u[1].y) + __uint_as_float(u[3].y)};
#pragma unroll
                    for (int i = 0; i < 4; i++) { v[i] += __shfl_xor_sync(~0u, v[i], 1); v[i] += __shfl_xor_sync(~0u, v[i], 2); }
                    ca = ln_coeffs(v[0] * (1.f / DM), v[1] * (1.f / DM));
                    cb = ln_coeffs(v[2] * (1.f / DM), v[3] * (1.f / DM));
                }
                const uint32_t ha = sb + OFF_Y + w * HALF + (lane >> 4) * 1024 + (2 * wi + ((lane >> 3) & 1)) * 128 + (lane & 7) * 16;
                const uint32_t sta = sb + M_ST + q * 16;
                const uint32_t* xg = act + RB_X1 + tile * 14336 + (lane >> 4) * 256 + wi * 64 + (lane & 15) * 4;
                uint32_t x[8];
                const uint32_t xs = sb + OFF_Y + w * HALF + (lane >> 4) * 1024 + wi * 256 + (lane & 15) * 16;
                uint4 st[2];
                auto load = [&](int s) {
                    if (s == 4) mbar_wait_c(BAR(B_XFULL + 4 + w), 1);
                    ldsm4(ha + s * 4096, x); ldsm4(ha + s * 4096 + 2048, x + 4);
                    st[0] = lds4(sta + s * 128); st[1] = lds4(sta + s * 128 + 64);
                };
                auto prep = [&](int s, uint32_t* f) {
                    if (__any_sync(~0u, min(min(min(x[0], x[1]), min(x[2], x[3])), min(min(x[4], x[5]), min(x[6], x[7]))) < 1u - sc)) {
                        WG_WAIT(0);
                        x1_fix(xg, xs, s);
                        ldsm4(ha + s * 4096, x); ldsm4(ha + s * 4096 + 2048, x + 4);
                    }
#pragma unroll
                    for (int i = 0; i < 2; i++) {
                        f[4 * i] = ln_mod(ln_norm(x[4 * i], ca), st[i].x, st[i].y); f[4 * i + 1] = ln_mod(ln_norm(x[4 * i + 1], cb), st[i].x, st[i].y);
                        f[4 * i + 2] = ln_mod(ln_norm(x[4 * i + 2], ca), st[i].z, st[i].w); f[4 * i + 3] = ln_mod(ln_norm(x[4 * i + 3], cb), st[i].z, st[i].w);
                    }
                    if (s < 13) load(s + 1);
                    stsm4(ha + s * 4096, f[0], f[1], f[2], f[3]); stsm4(ha + s * 4096 + 2048, f[4], f[5], f[6], f[7]);
                };
                float ac[128];
                uint32_t fr[3][8];
                uint64_t bd = (DB128 & ~0xFFFFFFFFull) | mkdesc(sb, DB128);
                reg_def<128>(ac);
                WAIT(B_GFULL + 2 + w, 0);
                load(0);
                prep(0, fr[0]);
                PROFC(17);
#pragma unroll
                for (int s = 0; s < 14; s++) {
                    const uint32_t* f = fr[s % 3];
                    WAIT(B_FULL + g1_slot(s), s >= 7);
                    WG_FENCE();
                    wgmma_rl_256(ac, f[0], f[1], f[2], f[3], bd, s != 0);
                    wgmma_rl_256(ac, f[4], f[5], f[6], f[7], bd + 128, 1);
                    bd += s == 6 ? p.zero - 6 * 1024ull : 1024;
                    WG_COMMIT();
                    if (s < 13) prep(s + 1, fr[(s + 1) % 3]);
                    if (s > 0) { WG_WAIT(1); warp_arrive(BAR(B_EMPTY + g1_slot(s - 1))); }
                }
                fence_async_smem();
                PROFC(18);
                WG_WAIT(0);
                reg_fence<128>(ac);
                warp_arrive(BAR(B_EMPTY + 6));
#pragma unroll
                for (int g = 0; g < 16; g++) {
                    h2a[2 * g] = hmul2(pack2_relu(ac[4 * g], ac[4 * g + 1]), pack2(ac[64 + 4 * g], ac[64 + 4 * g + 1]));
                    h2a[2 * g + 1] = hmul2(pack2_relu(ac[4 * g + 2], ac[4 * g + 3]), pack2(ac[64 + 4 * g + 2], ac[64 + 4 * g + 3]));
                }
                bar_sync(1 + w, 128);
            } else reg_def<32>(h2a);
            PROFC(19);
            if (RUN(5)) {
                float ac[64];
                reg_def<64>(ac);
                const uint32_t bx = mkdesc(sb, dconst(8192, 1024, 1));
#pragma unroll kB
                for (int s = 0; s < 7; s++) {
                    WAIT(B_FULL + s, 0);
                    const uint32_t ad = a0 + s * 512, bd = bx + (slot_off(s) >> 4);
                    WG_FENCE();
#pragma unroll
                    for (int k = 0; k < 4; k++) wgmma_ss_128<DT, DB128>(ac, ad + k * 128, bd + k * 128, (s | k) != 0);
                    WG_COMMIT();
                    if (s == 1) {
#pragma unroll
                        for (int g = 0; g < 16; g++) { h2g[(fa / 8 + g) * 512] = h2a[2 * g]; h2g[(fa / 8 + g) * 512 + 32] = h2a[2 * g + 1]; }
                        warp_arrive(BAR(B_PUB + 6));
                    }
                    if (s > 0) { WG_WAIT(1); warp_arrive(BAR(B_EMPTY + s - 1)); }
                }
                WG_WAIT(0);
                reg_fence<64>(ac);
                warp_arrive(BAR(B_EMPTY + 6));
#pragma unroll
                for (int g = 0; g < 8; g++) {
                    h2b[2 * g] = hmul2(pack2_relu(ac[4 * g], ac[4 * g + 1]), pack2(ac[32 + 4 * g], ac[32 + 4 * g + 1]));
                    h2b[2 * g + 1] = hmul2(pack2_relu(ac[4 * g + 2], ac[4 * g + 3]), pack2(ac[32 + 4 * g + 2], ac[32 + 4 * g + 3]));
                }
            } else reg_def<16>(h2b);
            PROFC(27);
            if (RUN(6)) {
                float ac[32];
                reg_def<32>(ac);
                const uint32_t bx = mkdesc(sb, dconst(4096, 512, 2));
#pragma unroll kC
                for (int s = 0; s < 7; s++) {
                    WAIT(B_FULL + s, 1);
                    const uint32_t ad = a0 + s * 512, bd = bx + (slot_off(s) >> 4);
                    WG_FENCE();
#pragma unroll
                    for (int k = 0; k < 4; k++) wgmma_ss_64<DT, dconst(4096, 512, 2)>(ac, ad + k * 128, bd + k * 64, (s | k) != 0);
                    WG_COMMIT();
                    if (s == 1) {
#pragma unroll
                        for (int g = 0; g < 8; g++) { h2g[(fb / 8 + g) * 512] = h2b[2 * g]; h2g[(fb / 8 + g) * 512 + 32] = h2b[2 * g + 1]; }
                        warp_arrive(BAR(B_PUB + 7));
                    }
                    if (s > 0) { WG_WAIT(1); warp_arrive(BAR(B_EMPTY + s - 1)); }
                }
                WG_WAIT(0);
                reg_fence<32>(ac);
                __syncwarp();
                if (lane < 6) mbar_arrive(BAR(B_EMPTY + 6 + lane));
                PROFC(20);
#pragma unroll
                for (int g = 0; g < 4; g++) {
                    h2b[16 + 2 * g] = hmul2(pack2_relu(ac[4 * g], ac[4 * g + 1]), pack2(ac[16 + 4 * g], ac[16 + 4 * g + 1]));
                    h2b[16 + 2 * g + 1] = hmul2(pack2_relu(ac[4 * g + 2], ac[4 * g + 3]), pack2(ac[16 + 4 * g + 2], ac[16 + 4 * g + 3]));
                    h2g[(fc / 8 + g) * 512] = h2b[16 + 2 * g]; h2g[(fc / 8 + g) * 512 + 32] = h2b[16 + 2 * g + 1];
                }
                warp_arrive(BAR(B_PUB + 8));
                asm volatile("barrier.cluster.wait.aligned;" ::: "memory");
                if (lane == 0 && !sc) {
                    uint32_t rb;
                    asm volatile("mapa.shared::cluster.u32 %0, %1, %2;" : "=r"(rb) : "r"(BAR(B_PEER)), "r"(kh ^ 1));
                    asm volatile("mbarrier.arrive.relaxed.cluster.shared::cluster.b64 _, [%0];" ::"r"(rb) : "memory");
                }
            } else reg_def<8>(h2b + 16);
        }
        PROFC(21);
        if (RUN(7)) {
            float ac[56];
            reg_def<56>(ac);
            constexpr uint64_t DAN = dconst(2048, 128, 0);
            constexpr uint64_t DW = dconst(128, 512, 0);
            const uint32_t bx = mkdesc(sb, DW);
            uint32_t ad = mkdesc(sb + 8192 + w * 1024, DAN), bd = bx, fb_ = BAR(B_FULL), eb_ = BAR(B_DUMMY), par = 0, first = 0;
            auto next = [&]() {
                WG_COMMIT();
                WG_WAIT(1);
                warp_arrive(eb_);
                eb_ = fb_ + 8 * (B_EMPTY - B_FULL);
                ad += 1024; bd += 1024; fb_ += 8; first = 1;
                if (fb_ == BAR(B_FULL + 12)) { ad -= 12 * 1024; bd -= 12 * 1024; fb_ -= 96; par ^= 1; }
            };
#pragma unroll
            for (int ps = 0; ps < 3; ps++) {
#pragma unroll 1
                for (int sidx = 0; sidx < 4; sidx++) {
                    if (sidx == nq) {
#pragma unroll
                        for (int k = 0; k < (4 >> ps); k++) {
                            const uint32_t* hh = (ps == 0 ? h2a : ps == 1 ? h2b : h2b + 16) + 8 * k;
                            mbar_wait_c(fb_, par);
                            WG_FENCE();
                            wgmma_rs_112<DW>(ac, hh[0], hh[1], hh[2], hh[3], bd, first);
                            wgmma_rs_112<DW>(ac, hh[4], hh[5], hh[6], hh[7], bd + 16, 1);
                            next();
                        }
                    } else {
#pragma unroll 1
                        for (int k = 0; k < (4 >> ps); k++) {
                            mbar_wait_c(fb_, par);
                            WG_FENCE();
                            wgmma_ss_112<DAN, DW>(ac, ad, bd, first);
                            wgmma_ss_112<DAN, DW>(ac, ad + 256, bd + 16, 1);
                            next();
                        }
                    }
                }
                if (ps == 0) PROFC(22);
            }
            mbar_wait_cluster(BAR(B_PEER), sc);
            WG_WAIT(0);
            reg_fence<56>(ac);
            PROFC(24);
            uint32_t rdst, rbar;
            asm volatile("mapa.shared::cluster.u32 %0, %1, %2;" : "=r"(rdst) : "r"(sb + OFF_Y + (5 + w) * 16384 + t * 16), "r"(kh ^ 1 ^ sc));
            asm volatile("mapa.shared::cluster.u32 %0, %1, %2;" : "=r"(rbar) : "r"(BAR(B_XCH + w)), "r"(kh ^ 1 ^ sc));
#pragma unroll
            for (int g = 0; g < 7; g++) {
                const float v0 = ac[28 + 4 * g + 0], v1 = ac[28 + 4 * g + 1];
                const float v2 = ac[28 + 4 * g + 2], v3 = ac[28 + 4 * g + 3];
                if (!sc) asm volatile("st.async.shared::cluster.mbarrier::complete_tx::bytes.v4.f32 [%0], {%1,%2,%3,%4}, [%5];"
                             ::"r"(rdst + g * 2048), "f"(v0), "f"(v1), "f"(v2), "f"(v3), "r"(rbar) : "memory");
            }
            mbar_wait_cluster(BAR(B_XCH + w), sc);
            PROFC(25);
            uint32_t op[16];
#pragma unroll
            for (int g = 0; g < 7; g++) {
                const uint4 rv = *(const uint4*)(smem + OFF_Y + (5 + w) * 16384 + t * 16 + g * 2048);
                const float2 gb = *(const float2*)(smem + M_G + 224 + (8 * g + 2 * q) * 4);
                const float v0 = ac[4 * g + 0] + __uint_as_float(rv.x), v1 = ac[4 * g + 1] + __uint_as_float(rv.y);
                const float v2 = ac[4 * g + 2] + __uint_as_float(rv.z), v3 = ac[4 * g + 3] + __uint_as_float(rv.w);
                op[2 * g] = pack2(fmaf(gb.x, v0, bf_lo(x1p[2 * g])), fmaf(gb.y, v1, bf_hi(x1p[2 * g])));
                op[2 * g + 1] = pack2(fmaf(gb.x, v2, bf_lo(x1p[2 * g + 1])), fmaf(gb.y, v3, bf_hi(x1p[2 * g + 1])));
            }
            WAIT(B_EMPTY + 5, 0);
            const uint32_t oc = sb + OUT_STAGE + warp * 1792;
            const uint32_t oa = oc + (((lane >> 3) & 1) * 8 + (lane & 7)) * 112 + (lane >> 4) * 16;
            stsm4(oa, op[0], op[1], op[2], op[3]); stsm4(oa + 32, op[4], op[5], op[6], op[7]); stsm4(oa + 64, op[8], op[9], op[10], op[11]);
            asm volatile("stmatrix.sync.aligned.m8n8.x2.shared.b16 [%0], {%1,%2};" ::"r"(oa + 96), "r"(op[12]), "r"(op[13]));
            fence_async_smem();
            __syncwarp();
            asm volatile("{\n.reg .pred p;\nelect.sync _|p, 0xffffffff;\n@p cp.async.bulk.tensor.3d.global.shared::cta.bulk_group [%0, {%2, %3, %4}], [%1];\n"
                         "cp.async.bulk.commit_group;\ncp.async.bulk.wait_group.read 0;\n}" ::"l"(&p.om), "r"(oc), "r"(56 * j), "r"(128 * r + 64 * w + 16 * wi), "r"(0) : "memory");
        }
        PROFC(26);
        bar_sync(1 + w, 128);
        if (wi == 0) warp_arrive(BAR(B_DONE));
        return;
    }
    helper_late(p, r, j, warp PROF_ARGS);
}

#undef act
typedef CUresult (*EncodeFn)(CUtensorMap*, CUtensorMapDataType, cuuint32_t, void*, const cuuint64_t*, const cuuint64_t*, const cuuint32_t*,
                             const cuuint32_t*, CUtensorMapInterleave, CUtensorMapSwizzle, CUtensorMapL2promotion, CUtensorMapFloatOOBfill);

static void make_map(EncodeFn fn, CUtensorMap* m, const void* ptr, uint64_t d0, uint64_t d1, uint64_t d2, uint64_t s1, uint64_t s2,
                     uint32_t b0, uint32_t b1, uint32_t b2, CUtensorMapSwizzle sw) {
    cuuint64_t dims[3] = {d0, d1, d2}, strides[2] = {s1, s2};
    cuuint32_t box[3] = {b0, b1, b2}, es[3] = {1, 1, 1};
    CUresult rc = fn(m, CU_TENSOR_MAP_DATA_TYPE_BFLOAT16, 3, (void*)ptr, dims, strides, box, es, CU_TENSOR_MAP_INTERLEAVE_NONE, sw,
                     CU_TENSOR_MAP_L2_PROMOTION_L2_128B, CU_TENSOR_MAP_FLOAT_OOB_FILL_NONE);
    (void)rc;
}

extern "C" void kernel_launch(void* const* d_in, const int* in_sizes, int n_in, void* d_out, int out_size) {
    (void)in_sizes; (void)n_in; (void)out_size;
    static EncodeFn fn = nullptr;
    static uint32_t* act_base = nullptr;
    if (!fn) {
        cudaDriverEntryPointQueryResult st;
        cudaGetDriverEntryPoint("cuTensorMapEncodeTiled", (void**)&fn, cudaEnableDefault, &st);
        void* a = nullptr;
        cudaGetSymbolAddress(&a, g_act);
        act_base = (uint32_t*)(((uintptr_t)a + 0xFFFFF) & ~(uintptr_t)0xFFFFF);
        cudaFuncSetAttribute(fused_block_kernel, cudaFuncAttributeMaxDynamicSharedMemorySize, SMEM_BYTES);
    }
    Params p;
    p.x = (const bf16*)d_in[0];
    const bf16* wqkv = (const bf16*)d_in[1];
    p.wqkv = wqkv;
    p.wop = (const bf16*)d_in[2];
    p.wg = (const bf16*)d_in[4];
    p.wu = (const bf16*)d_in[5];
    p.wd = (const bf16*)d_in[6];
    p.c = (const bf16*)d_in[7];
    p.wmod = (const bf16*)d_in[8];
    p.out = (bf16*)d_out;
    p.zero = 0;
    p.actb = act_base;
    make_map(fn, &p.wm, p.wmod, 2688, 448, 1, 5376, 5376 * 448, 16, 224, 1, CU_TENSOR_MAP_SWIZZLE_NONE);
    make_map(fn, &p.wm2, p.wmod, 2688, 448, 1, 5376, 5376 * 448, 32, 224, 1, CU_TENSOR_MAP_SWIZZLE_NONE);
    make_map(fn, &p.om, p.out, 448, 2048, 1, 896, 896 * 2048, 56, 16, 1, CU_TENSOR_MAP_SWIZZLE_NONE);
    make_map(fn, &p.xm, p.x, 448, 2048, 1, 896, 896 * 2048, 64, 128, 1, CU_TENSOR_MAP_SWIZZLE_128B);
    make_map(fn, &p.qkv, wqkv, 1344, 448, 1, 2688, 2688 * 448, 64, 224, 1, CU_TENSOR_MAP_SWIZZLE_128B);
    make_map(fn, &p.wo, p.wop, 448, 448, 1, 896, 896 * 448, 64, 224, 1, CU_TENSOR_MAP_SWIZZLE_128B);
    make_map(fn, &p.ga, p.wg, 64, 448, 28, 3584, 128, 64, 32, 2, CU_TENSOR_MAP_SWIZZLE_128B);
    make_map(fn, &p.ua, p.wu, 64, 448, 28, 3584, 128, 64, 32, 2, CU_TENSOR_MAP_SWIZZLE_128B);
    make_map(fn, &p.gb, p.wg, 64, 448, 28, 3584, 128, 64, 64, 1, CU_TENSOR_MAP_SWIZZLE_128B);
    make_map(fn, &p.ub, p.wu, 64, 448, 28, 3584, 128, 64, 64, 1, CU_TENSOR_MAP_SWIZZLE_128B);
    make_map(fn, &p.gc, p.wg, 32, 448, 56, 3584, 64, 32, 64, 1, CU_TENSOR_MAP_SWIZZLE_64B);
    make_map(fn, &p.uc, p.wu, 32, 448, 56, 3584, 64, 32, 64, 1, CU_TENSOR_MAP_SWIZZLE_64B);
    make_map(fn, &p.dn, p.wd, 8, 1792, 56, 896, 16, 8, 32, 7, CU_TENSOR_MAP_SWIZZLE_NONE);
    fused_block_kernel<<<GRID, 384, SMEM_BYTES>>>(p);
}
```

```cpp
#include <cuda_runtime.h>
#include <cuda_bf16.h>
#include <cuda.h>
#include <stdint.h>

typedef __nv_bfloat16 bf16;

template<uint64_t CA, uint64_t CB> __device__ __forceinline__ void wgmma_sk_160(float* d, uint32_t da, uint32_t db, int sd) {
  asm volatile("{\n.reg .pred p;\n.reg .b64 a, b;\nsetp.ne.b32 p, %82, 0;\nmov.b64 a, {%80, %83};\nmov.b64 b, {%81, %84};\n"
    "wgmma.mma_async.sync.aligned.m64n160k16.f32.bf16.bf16 {%0,%1,%2,%3,%4,%5,%6,%7,%8,%9,%10,%11,%12,%13,%14,%15,%16,%17,%18,%19,%20,%21,%22,%23,%24,%25,%26,%27,%28,%29,%30,%31,%32,%33,%34,%35,%36,%37,%38,%39,%40,%41,%42,%43,%44,%45,%46,%47,%48,%49,%50,%51,%52,%53,%54,%55,%56,%57,%58,%59,%60,%61,%62,%63,%64,%65,%66,%67,%68,%69,%70,%71,%72,%73,%74,%75,%76,%77,%78,%79}, a, b, p, 1, 1, 0, 0;\n}\n"
    : "+f"(d[0]),"+f"(d[1]),"+f"(d[2]),"+f"(d[3]),"+f"(d[4]),"+f"(d[5]),"+f"(d[6]),"+f"(d[7]),"+f"(d[8]),"+f"(d[9]),"+f"(d[10]),"+f"(d[11]),"+f"(d[12]),"+f"(d[13]),"+f"(d[14]),"+f"(d[15]),"+f"(d[16]),"+f"(d[17]),"+f"(d[18]),"+f"(d[19]),"+f"(d[20]),"+f"(d[21]),"+f"(d[22]),"+f"(d[23]),"+f"(d[24]),"+f"(d[25]),"+f"(d[26]),"+f"(d[27]),"+f"(d[28]),"+f"(d[29]),"+f"(d[30]),"+f"(d[31]),"+f"(d[32]),"+f"(d[33]),"+f"(d[34]),"+f"(d[35]),"+f"(d[36]),"+f"(d[37]),"+f"(d[38]),"+f"(d[39]),"+f"(d[40]),"+f"(d[41]),"+f"(d[42]),"+f"(d[43]),"+f"(d[44]),"+f"(d[45]),"+f"(d[46]),"+f"(d[47]),"+f"(d[48]),"+f"(d[49]),"+f"(d[50]),"+f"(d[51]),"+f"(d[52]),"+f"(d[53]),"+f"(d[54]),"+f"(d[55]),"+f"(d[56]),"+f"(d[57]),"+f"(d[58]),"+f"(d[59]),"+f"(d[60]),"+f"(d[61]),"+f"(d[62]),"+f"(d[63]),"+f"(d[64]),"+f"(d[65]),"+f"(d[66]),"+f"(d[67]),"+f"(d[68]),"+f"(d[69]),"+f"(d[70]),"+f"(d[71]),"+f"(d[72]),"+f"(d[73]),"+f"(d[74]),"+f"(d[75]),"+f"(d[76]),"+f"(d[77]),"+f"(d[78]),"+f"(d[79])
    : "r"(da), "r"(db), "r"(sd), "n"((uint32_t)(CA >> 32)), "n"((uint32_t)(CB >> 32)));
}
__device__ __forceinline__ void wgmma_rl_56(float* d, uint32_t a0, uint32_t a1, uint32_t a2, uint32_t a3, uint64_t db, int sd) {
  asm volatile("{\n.reg .pred p;\nsetp.ne.b32 p, %33, 0;\n"
    "wgmma.mma_async.sync.aligned.m64n56k16.f32.bf16.bf16 {%0,%1,%2,%3,%4,%5,%6,%7,%8,%9,%10,%11,%12,%13,%14,%15,%16,%17,%18,%19,%20,%21,%22,%23,%24,%25,%26,%27}, {%28,%29,%30,%31}, %32, p, 1, 1, 1;\n}\n"
    : "+f"(d[0]),"+f"(d[1]),"+f"(d[2]),"+f"(d[3]),"+f"(d[4]),"+f"(d[5]),"+f"(d[6]),"+f"(d[7]),"+f"(d[8]),"+f"(d[9]),"+f"(d[10]),"+f"(d[11]),"+f"(d[12]),"+f"(d[13]),"+f"(d[14]),"+f"(d[15]),"+f"(d[16]),"+f"(d[17]),"+f"(d[18]),"+f"(d[19]),"+f"(d[20]),"+f"(d[21]),"+f"(d[22]),"+f"(d[23]),"+f"(d[24]),"+f"(d[25]),"+f"(d[26]),"+f"(d[27])
    : "r"(a0), "r"(a1), "r"(a2), "r"(a3), "l"(db), "r"(sd));
}
template<uint64_t CA, uint64_t CB> __device__ __forceinline__ void wgmma_ss_56(float* d, uint32_t da, uint32_t db, int sd) {
  asm volatile("{\n.reg .pred p;\n.reg .b64 a, b;\nsetp.ne.b32 p, %30, 0;\nmov.b64 a, {%28, %31};\nmov.b64 b, {%29, %32};\n"
    "wgmma.mma_async.sync.aligned.m64n56k16.f32.bf16.bf16 {%0,%1,%2,%3,%4,%5,%6,%7,%8,%9,%10,%11,%12,%13,%14,%15,%16,%17,%18,%19,%20,%21,%22,%23,%24,%25,%26,%27}, a, b, p, 1, 1, 0, 1;\n}\n"
    : "+f"(d[0]),"+f"(d[1]),"+f"(d[2]),"+f"(d[3]),"+f"(d[4]),"+f"(d[5]),"+f"(d[6]),"+f"(d[7]),"+f"(d[8]),"+f"(d[9]),"+f"(d[10]),"+f"(d[11]),"+f"(d[12]),"+f"(d[13]),"+f"(d[14]),"+f"(d[15]),"+f"(d[16]),"+f"(d[17]),"+f"(d[18]),"+f"(d[19]),"+f"(d[20]),"+f"(d[21]),"+f"(d[22]),"+f"(d[23]),"+f"(d[24]),"+f"(d[25]),"+f"(d[26]),"+f"(d[27])
    : "r"(da), "r"(db), "r"(sd), "n"((uint32_t)(CA >> 32)), "n"((uint32_t)(CB >> 32)));
}
__device__ __forceinline__ void wgmma_rl_256(float* d, uint32_t a0, uint32_t a1, uint32_t a2, uint32_t a3, uint64_t db, int sd) {
  asm volatile("{\n.reg .pred p;\nsetp.ne.b32 p, %133, 0;\n"
    "wgmma.mma_async.sync.aligned.m64n256k16.f32.bf16.bf16 {%0,%1,%2,%3,%4,%5,%6,%7,%8,%9,%10,%11,%12,%13,%14,%15,%16,%17,%18,%19,%20,%21,%22,%23,%24,%25,%26,%27,%28,%29,%30,%31,%32,%33,%34,%35,%36,%37,%38,%39,%40,%41,%42,%43,%44,%45,%46,%47,%48,%49,%50,%51,%52,%53,%54,%55,%56,%57,%58,%59,%60,%61,%62,%63,%64,%65,%66,%67,%68,%69,%70,%71,%72,%73,%74,%75,%76,%77,%78,%79,%80,%81,%82,%83,%84,%85,%86,%87,%88,%89,%90,%91,%92,%93,%94,%95,%96,%97,%98,%99,%100,%101,%102,%103,%104,%105,%106,%107,%108,%109,%110,%111,%112,%113,%114,%115,%116,%117,%118,%119,%120,%121,%122,%123,%124,%125,%126,%127}, {%128,%129,%130,%131}, %132, p, 1, 1, 1;\n}\n"
    : "+f"(d[0]),"+f"(d[1]),"+f"(d[2]),"+f"(d[3]),"+f"(d[4]),"+f"(d[5]),"+f"(d[6]),"+f"(d[7]),"+f"(d[8]),"+f"(d[9]),"+f"(d[10]),"+f"(d[11]),"+f"(d[12]),"+f"(d[13]),"+f"(d[14]),"+f"(d[15]),"+f"(d[16]),"+f"(d[17]),"+f"(d[18]),"+f"(d[19]),"+f"(d[20]),"+f"(d[21]),"+f"(d[22]),"+f"(d[23]),"+f"(d[24]),"+f"(d[25]),"+f"(d[26]),"+f"(d[27]),"+f"(d[28]),"+f"(d[29]),"+f"(d[30]),"+f"(d[31]),"+f"(d[32]),"+f"(d[33]),"+f"(d[34]),"+f"(d[35]),"+f"(d[36]),"+f"(d[37]),"+f"(d[38]),"+f"(d[39]),"+f"(d[40]),"+f"(d[41]),"+f"(d[42]),"+f"(d[43]),"+f"(d[44]),"+f"(d[45]),"+f"(d[46]),"+f"(d[47]),"+f"(d[48]),"+f"(d[49]),"+f"(d[50]),"+f"(d[51]),"+f"(d[52]),"+f"(d[53]),"+f"(d[54]),"+f"(d[55]),"+f"(d[56]),"+f"(d[57]),"+f"(d[58]),"+f"(d[59]),"+f"(d[60]),"+f"(d[61]),"+f"(d[62]),"+f"(d[63]),"+f"(d[64]),"+f"(d[65]),"+f"(d[66]),"+f"(d[67]),"+f"(d[68]),"+f"(d[69]),"+f"(d[70]),"+f"(d[71]),"+f"(d[72]),"+f"(d[73]),"+f"(d[74]),"+f"(d[75]),"+f"(d[76]),"+f"(d[77]),"+f"(d[78]),"+f"(d[79]),"+f"(d[80]),"+f"(d[81]),"+f"(d[82]),"+f"(d[83]),"+f"(d[84]),"+f"(d[85]),"+f"(d[86]),"+f"(d[87]),"+f"(d[88]),"+f"(d[89]),"+f"(d[90]),"+f"(d[91]),"+f"(d[92]),"+f"(d[93]),"+f"(d[94]),"+f"(d[95]),"+f"(d[96]),"+f"(d[97]),"+f"(d[98]),"+f"(d[99]),"+f"(d[100]),"+f"(d[101]),"+f"(d[102]),"+f"(d[103]),"+f"(d[104]),"+f"(d[105]),"+f"(d[106]),"+f"(d[107]),"+f"(d[108]),"+f"(d[109]),"+f"(d[110]),"+f"(d[111]),"+f"(d[112]),"+f"(d[113]),"+f"(d[114]),"+f"(d[115]),"+f"(d[116]),"+f"(d[117]),"+f"(d[118]),"+f"(d[119]),"+f"(d[120]),"+f"(d[121]),"+f"(d[122]),"+f"(d[123]),"+f"(d[124]),"+f"(d[125]),"+f"(d[126]),"+f"(d[127])
    : "r"(a0), "r"(a1), "r"(a2), "r"(a3), "l"(db), "r"(sd));
}
template<uint64_t CA, uint64_t CB> __device__ __forceinline__ void wgmma_ss_128(float* d, uint32_t da, uint32_t db, int sd) {
  asm volatile("{\n.reg .pred p;\n.reg .b64 a, b;\nsetp.ne.b32 p, %66, 0;\nmov.b64 a, {%64, %67};\nmov.b64 b, {%65, %68};\n"
    "wgmma.mma_async.sync.aligned.m64n128k16.f32.bf16.bf16 {%0,%1,%2,%3,%4,%5,%6,%7,%8,%9,%10,%11,%12,%13,%14,%15,%16,%17,%18,%19,%20,%21,%22,%23,%24,%25,%26,%27,%28,%29,%30,%31,%32,%33,%34,%35,%36,%37,%38,%39,%40,%41,%42,%43,%44,%45,%46,%47,%48,%49,%50,%51,%52,%53,%54,%55,%56,%57,%58,%59,%60,%61,%62,%63}, a, b, p, 1, 1, 0, 1;\n}\n"
    : "+f"(d[0]),"+f"(d[1]),"+f"(d[2]),"+f"(d[3]),"+f"(d[4]),"+f"(d[5]),"+f"(d[6]),"+f"(d[7]),"+f"(d[8]),"+f"(d[9]),"+f"(d[10]),"+f"(d[11]),"+f"(d[12]),"+f"(d[13]),"+f"(d[14]),"+f"(d[15]),"+f"(d[16]),"+f"(d[17]),"+f"(d[18]),"+f"(d[19]),"+f"(d[20]),"+f"(d[21]),"+f"(d[22]),"+f"(d[23]),"+f"(d[24]),"+f"(d[25]),"+f"(d[26]),"+f"(d[27]),"+f"(d[28]),"+f"(d[29]),"+f"(d[30]),"+f"(d[31]),"+f"(d[32]),"+f"(d[33]),"+f"(d[34]),"+f"(d[35]),"+f"(d[36]),"+f"(d[37]),"+f"(d[38]),"+f"(d[39]),"+f"(d[40]),"+f"(d[41]),"+f"(d[42]),"+f"(d[43]),"+f"(d[44]),"+f"(d[45]),"+f"(d[46]),"+f"(d[47]),"+f"(d[48]),"+f"(d[49]),"+f"(d[50]),"+f"(d[51]),"+f"(d[52]),"+f"(d[53]),"+f"(d[54]),"+f"(d[55]),"+f"(d[56]),"+f"(d[57]),"+f"(d[58]),"+f"(d[59]),"+f"(d[60]),"+f"(d[61]),"+f"(d[62]),"+f"(d[63])
    : "r"(da), "r"(db), "r"(sd), "n"((uint32_t)(CA >> 32)), "n"((uint32_t)(CB >> 32)));
}
template<uint64_t CA, uint64_t CB> __device__ __forceinline__ void wgmma_ss_64(float* d, uint32_t da, uint32_t db, int sd) {
  asm volatile("{\n.reg .pred p;\n.reg .b64 a, b;\nsetp.ne.b32 p, %34, 0;\nmov.b64 a, {%32, %35};\nmov.b64 b, {%33, %36};\n"
    "wgmma.mma_async.sync.aligned.m64n64k16.f32.bf16.bf16 {%0,%1,%2,%3,%4,%5,%6,%7,%8,%9,%10,%11,%12,%13,%14,%15,%16,%17,%18,%19,%20,%21,%22,%23,%24,%25,%26,%27,%28,%29,%30,%31}, a, b, p, 1, 1, 0, 1;\n}\n"
    : "+f"(d[0]),"+f"(d[1]),"+f"(d[2]),"+f"(d[3]),"+f"(d[4]),"+f"(d[5]),"+f"(d[6]),"+f"(d[7]),"+f"(d[8]),"+f"(d[9]),"+f"(d[10]),"+f"(d[11]),"+f"(d[12]),"+f"(d[13]),"+f"(d[14]),"+f"(d[15]),"+f"(d[16]),"+f"(d[17]),"+f"(d[18]),"+f"(d[19]),"+f"(d[20]),"+f"(d[21]),"+f"(d[22]),"+f"(d[23]),"+f"(d[24]),"+f"(d[25]),"+f"(d[26]),"+f"(d[27]),"+f"(d[28]),"+f"(d[29]),"+f"(d[30]),"+f"(d[31])
    : "r"(da), "r"(db), "r"(sd), "n"((uint32_t)(CA >> 32)), "n"((uint32_t)(CB >> 32)));
}
template<uint64_t CA, uint64_t CB> __device__ __forceinline__ void wgmma_ss_112(float* d, uint32_t da, uint32_t db, int sd) {
  asm volatile("{\n.reg .pred p;\n.reg .b64 a, b;\nsetp.ne.b32 p, %58, 0;\nmov.b64 a, {%56, %59};\nmov.b64 b, {%57, %60};\n"
    "wgmma.mma_async.sync.aligned.m64n112k16.f32.bf16.bf16 {%0,%1,%2,%3,%4,%5,%6,%7,%8,%9,%10,%11,%12,%13,%14,%15,%16,%17,%18,%19,%20,%21,%22,%23,%24,%25,%26,%27,%28,%29,%30,%31,%32,%33,%34,%35,%36,%37,%38,%39,%40,%41,%42,%43,%44,%45,%46,%47,%48,%49,%50,%51,%52,%53,%54,%55}, a, b, p, 1, 1, 0, 1;\n}\n"
    : "+f"(d[0]),"+f"(d[1]),"+f"(d[2]),"+f"(d[3]),"+f"(d[4]),"+f"(d[5]),"+f"(d[6]),"+f"(d[7]),"+f"(d[8]),"+f"(d[9]),"+f"(d[10]),"+f"(d[11]),"+f"(d[12]),"+f"(d[13]),"+f"(d[14]),"+f"(d[15]),"+f"(d[16]),"+f"(d[17]),"+f"(d[18]),"+f"(d[19]),"+f"(d[20]),"+f"(d[21]),"+f"(d[22]),"+f"(d[23]),"+f"(d[24]),"+f"(d[25]),"+f"(d[26]),"+f"(d[27]),"+f"(d[28]),"+f"(d[29]),"+f"(d[30]),"+f"(d[31]),"+f"(d[32]),"+f"(d[33]),"+f"(d[34]),"+f"(d[35]),"+f"(d[36]),"+f"(d[37]),"+f"(d[38]),"+f"(d[39]),"+f"(d[40]),"+f"(d[41]),"+f"(d[42]),"+f"(d[43]),"+f"(d[44]),"+f"(d[45]),"+f"(d[46]),"+f"(d[47]),"+f"(d[48]),"+f"(d[49]),"+f"(d[50]),"+f"(d[51]),"+f"(d[52]),"+f"(d[53]),"+f"(d[54]),"+f"(d[55])
    : "r"(da), "r"(db), "r"(sd), "n"((uint32_t)(CA >> 32)), "n"((uint32_t)(CB >> 32)));
}
__device__ __forceinline__ void wgmma_rl_112(float* d, uint32_t a0, uint32_t a1, uint32_t a2, uint32_t a3, uint64_t db, int sd) {
  asm volatile("{\n.reg .pred p;\nsetp.ne.b32 p, %61, 0;\n"
    "wgmma.mma_async.sync.aligned.m64n112k16.f32.bf16.bf16 {%0,%1,%2,%3,%4,%5,%6,%7,%8,%9,%10,%11,%12,%13,%14,%15,%16,%17,%18,%19,%20,%21,%22,%23,%24,%25,%26,%27,%28,%29,%30,%31,%32,%33,%34,%35,%36,%37,%38,%39,%40,%41,%42,%43,%44,%45,%46,%47,%48,%49,%50,%51,%52,%53,%54,%55}, {%56,%57,%58,%59}, %60, p, 1, 1, 1;\n}\n"
    : "+f"(d[0]),"+f"(d[1]),"+f"(d[2]),"+f"(d[3]),"+f"(d[4]),"+f"(d[5]),"+f"(d[6]),"+f"(d[7]),"+f"(d[8]),"+f"(d[9]),"+f"(d[10]),"+f"(d[11]),"+f"(d[12]),"+f"(d[13]),"+f"(d[14]),"+f"(d[15]),"+f"(d[16]),"+f"(d[17]),"+f"(d[18]),"+f"(d[19]),"+f"(d[20]),"+f"(d[21]),"+f"(d[22]),"+f"(d[23]),"+f"(d[24]),"+f"(d[25]),"+f"(d[26]),"+f"(d[27]),"+f"(d[28]),"+f"(d[29]),"+f"(d[30]),"+f"(d[31]),"+f"(d[32]),"+f"(d[33]),"+f"(d[34]),"+f"(d[35]),"+f"(d[36]),"+f"(d[37]),"+f"(d[38]),"+f"(d[39]),"+f"(d[40]),"+f"(d[41]),"+f"(d[42]),"+f"(d[43]),"+f"(d[44]),"+f"(d[45]),"+f"(d[46]),"+f"(d[47]),"+f"(d[48]),"+f"(d[49]),"+f"(d[50]),"+f"(d[51]),"+f"(d[52]),"+f"(d[53]),"+f"(d[54]),"+f"(d[55])
    : "r"(a0), "r"(a1), "r"(a2), "r"(a3), "l"(db), "r"(sd));
}

constexpr int DM = 448;
constexpr int NCTA = 128;
#define WIN 6
#define NPRE 14
#define VPRE 3
constexpr int SPIN_LIMIT = 1 << 22;

constexpr uint32_t OFF_X = 0, OFF_Y = 114688, OFF_MISC = 229376, SMEM_BYTES = 232448;
constexpr uint32_t Y_VR = 0, Y_K = 28672, Y_KOWN = 57344, Y_VOWN = 71680, Y_Q = 86016;
constexpr uint32_t HALF = 57344;
constexpr uint32_t X_STAT = 49152;
constexpr uint32_t OUT_STAGE = 16384;
constexpr uint32_t M_BAR = OFF_MISC;
constexpr uint32_t M_ST = OFF_MISC + 512;
constexpr uint32_t M_G = OFF_MISC + 2304;
constexpr uint32_t M_EPOCH = OFF_MISC + 3040;
enum { B_XFULL = 0, B_FULLK = 7, B_FULLV = 8, B_FULLQ, B_KRFULL, B_VRFULL, B_WOFULL, B_XCH, B_MOD1 = 15, B_FULL = 16, B_WMFULL = 30,
       B_EMPTY = 32, B_XFREE = B_EMPTY + 12, B_GEMV, B_PEER,
       B_PUB = 47,
       B_WMFREE = 56, B_HRDY, B_GFULL = B_HRDY + 3, B_DONE = 31, B_DUMMY = B_GEMV };

__device__ uint32_t g_ticket;
__device__ __align__(128) uint32_t g_mod[8 * 6 * DM];
__device__ __align__(128) uint32_t g_flag[144 * 128];
constexpr int RB_WORDS = 262144, RB_KV = 0, RB_O = 57344, RB_X1 = 86016, RB_H2 = 143360, RB_ST = 258048;
__device__ __align__(128) uint32_t g_act[17 * RB_WORDS];
__device__ __align__(128) uint32_t g_wd[56 * 4 * 1792];
#define PROFH(id)
#define PROFH1(id)
#define PROFC(id)

struct alignas(64) Params {
    CUtensorMap wm, wm2, om, xm, qkv, wo, ga, ua, gb, ub, gc, uc, dn;
    const bf16 *x, *c, *wqkv, *wmod, *wg, *wu, *wd, *wop;
    bf16* out;
    uint32_t* actb;
    uint32_t zero;
};

__device__ __forceinline__ void mbar_init(uint32_t bar, int cnt) { asm volatile("mbarrier.init.shared::cta.b64 [%0], %1;" ::"r"(bar), "r"(cnt) : "memory"); }
__device__ __forceinline__ void mbar_arrive(uint32_t bar) { asm volatile("mbarrier.arrive.shared::cta.b64 _, [%0];" ::"r"(bar) : "memory"); }
__device__ __forceinline__ void mbar_wait(uint32_t bar, uint32_t parity) {
    uint32_t ok; int n = 0;
    do {
        asm volatile("{\n.reg .pred p;\nmbarrier.try_wait.parity.shared::cta.b64 p, [%1], %2;\nselp.u32 %0, 1, 0, p;\n}" : "=r"(ok) : "r"(bar), "r"(parity) : "memory");
        if (++n > SPIN_LIMIT) __trap();
    } while (!ok);
}
__device__ __forceinline__ void mbar_wait_c(uint32_t bar, uint32_t parity) {
    asm volatile("{\n.reg .pred p;\nWL:\nmbarrier.try_wait.parity.shared::cta.b64 p, [%0], %1, 0x989680;\n@!p bra WL;\n}" ::"r"(bar), "r"(parity) : "memory");
}
__device__ __forceinline__ void mbar_wait_cluster(uint32_t bar, uint32_t parity) {
    asm volatile("{\n.reg .pred p;\nWL:\nmbarrier.try_wait.parity.acquire.cluster.shared::cta.b64 p, [%0], %1, 0x989680;\n@!p bra WL;\n}" ::"r"(bar), "r"(parity) : "memory");
}
__device__ __forceinline__ void warp_arrive(uint32_t bar) {
    __syncwarp();
    asm volatile("{\n.reg .pred p;\nelect.sync _|p, 0xffffffff;\n@p mbarrier.arrive.shared::cta.b64 _, [%0];\n}" ::"r"(bar) : "memory");
}
__device__ __forceinline__ int opaque(int v) { return __shfl_sync(~0u, v, 0); }
__device__ __forceinline__ int fresh_tid() { int v; asm volatile("mov.u32 %0, %%tid.x;" : "=r"(v)); return v; }
__device__ __forceinline__ void bar_sync(int id, int n) { asm volatile("bar.sync %0, %1;" ::"r"(id), "r"(n) : "memory"); }
__device__ __forceinline__ void bar_arrive(int id, int n) { asm volatile("bar.arrive %0, %1;" ::"r"(id), "r"(n) : "memory"); }
__device__ __forceinline__ void fence_async_smem() { asm volatile("fence.proxy.async.shared::cta;" ::: "memory"); }
__device__ __forceinline__ void fence_async_global() { asm volatile("fence.proxy.async.global;" ::: "memory"); }
__device__ __forceinline__ void fence_gpu() { asm volatile("fence.release.gpu;" ::: "memory"); }
__device__ __forceinline__ void expect_e(uint32_t bar, uint32_t bytes) {
    asm volatile("{\n.reg .pred p;\nelect.sync _|p, 0xffffffff;\n@p mbarrier.arrive.expect_tx.shared::cta.b64 _, [%0], %1;\n}" ::"r"(bar), "r"(bytes) : "memory");
}
__device__ __forceinline__ void tma3_e(uint32_t dst, const CUtensorMap* m, int c0, int c1, int c2, uint32_t bar) {
    asm volatile("{\n.reg .pred p;\nelect.sync _|p, 0xffffffff;\n@p cp.async.bulk.tensor.3d.shared::cluster.global.mbarrier::complete_tx::bytes [%0], [%1, {%3, %4, %5}], [%2];\n}"
                 ::"r"(dst), "l"(m), "r"(bar), "r"(c0), "r"(c1), "r"(c2) : "memory");
}
__device__ __forceinline__ void bulk_e(uint32_t dst, const void* src, uint32_t bytes, uint32_t bar) {
    asm volatile("{\n.reg .pred p;\nelect.sync _|p, 0xffffffff;\n@p cp.async.bulk.shared::cluster.global.mbarrier::complete_tx::bytes [%0], [%1], %2, [%3];\n}"
                 ::"r"(dst), "l"(src), "r"(bytes), "r"(bar) : "memory");
}
__device__ __forceinline__ void init_e(uint32_t bar, int cnt) {
    asm volatile("{\n.reg .pred p;\nelect.sync _|p, 0xffffffff;\n@p mbarrier.init.shared::cta.b64 [%0], %1;\n}" ::"r"(bar), "r"(cnt) : "memory");
}
__device__ __forceinline__ void l2_prefetch_e(const void* src, uint32_t bytes) {
    asm volatile("{\n.reg .pred p;\nelect.sync _|p, 0xffffffff;\n@p cp.async.bulk.prefetch.L2.global [%0], %1;\n}" ::"l"(src), "r"(bytes) : "memory");
}
__device__ __forceinline__ uint32_t ld_relaxed(const uint32_t* p) { uint32_t v; asm volatile("ld.relaxed.gpu.global.u32 %0, [%1];" : "=r"(v) : "l"(p) : "memory"); return v; }
__device__ __forceinline__ void st_relaxed(uint32_t* p, uint32_t v) { asm volatile("st.relaxed.gpu.global.u32 [%0], %1;" ::"l"(p), "r"(v) : "memory"); }
__device__ __forceinline__ uint4 ld_relaxed4(const uint4* p) { uint4 v; asm volatile("ld.relaxed.gpu.global.v4.u32 {%0,%1,%2,%3}, [%4];" : "=r"(v.x), "=r"(v.y), "=r"(v.z), "=r"(v.w) : "l"(p) : "memory"); return v; }
__device__ __forceinline__ uint4 lds4(uint32_t a) { uint4 v; asm volatile("ld.shared.v4.u32 {%0,%1,%2,%3}, [%4];" : "=r"(v.x), "=r"(v.y), "=r"(v.z), "=r"(v.w) : "r"(a) : "memory"); return v; }
__device__ __forceinline__ float2 lds2f(uint32_t a) { float2 v; asm volatile("ld.shared.v2.f32 {%0,%1}, [%2];" : "=f"(v.x), "=f"(v.y) : "r"(a) : "memory"); return v; }
__device__ __forceinline__ uint32_t lds1(uint32_t a) { uint32_t v; asm volatile("ld.shared.u32 %0, [%1];" : "=r"(v) : "r"(a) : "memory"); return v; }
__device__ __forceinline__ void sts4(uint32_t a, uint4 v) { asm volatile("st.shared.v4.u32 [%0], {%1,%2,%3,%4};" ::"r"(a), "r"(v.x), "r"(v.y), "r"(v.z), "r"(v.w) : "memory"); }
__device__ __forceinline__ void sts1(uint32_t a, uint32_t v) { asm volatile("st.shared.u32 [%0], %1;" ::"r"(a), "r"(v) : "memory"); }
__device__ __forceinline__ void stsm4(uint32_t a, uint32_t r0, uint32_t r1, uint32_t r2, uint32_t r3) {
    asm volatile("stmatrix.sync.aligned.m8n8.x4.shared.b16 [%0], {%1,%2,%3,%4};" ::"r"(a), "r"(r0), "r"(r1), "r"(r2), "r"(r3));
}
__device__ __forceinline__ uint32_t pack2(float lo, float hi) { uint32_t r; asm("cvt.rn.bf16x2.f32 %0, %1, %2;" : "=r"(r) : "f"(hi), "f"(lo)); return r; }
__device__ __forceinline__ uint32_t pack2_relu(float lo, float hi) { uint32_t r; asm("cvt.rn.relu.bf16x2.f32 %0, %1, %2;" : "=r"(r) : "f"(hi), "f"(lo)); return r; }
__device__ __forceinline__ uint32_t hfma2(uint32_t a, uint32_t b, uint32_t c) { uint32_t r; asm("fma.rn.bf16x2 %0, %1, %2, %3;" : "=r"(r) : "r"(a), "r"(b), "r"(c)); return r; }
__device__ __forceinline__ uint32_t hmul2(uint32_t a, uint32_t b) { uint32_t r; asm("mul.rn.bf16x2 %0, %1, %2;" : "=r"(r) : "r"(a), "r"(b)); return r; }
__device__ __forceinline__ float bf_lo(uint32_t v) { return __uint_as_float(v << 16); }
__device__ __forceinline__ float bf_hi(uint32_t v) { return __uint_as_float(v & 0xFFFF0000u); }
__device__ __forceinline__ float bf_round(float v) { return bf_lo(pack2(v, 0.f)); }
__device__ __forceinline__ float ex2(float x) { float r; asm("ex2.approx.ftz.f32 %0, %1;" : "=f"(r) : "f"(x)); return r; }
__device__ __forceinline__ void mma16816(float* d, uint32_t a0, uint32_t a1, uint32_t a2, uint32_t a3, uint32_t b0, uint32_t b1) {
    asm("mma.sync.aligned.m16n8k16.row.col.f32.bf16.bf16.f32 {%0,%1,%2,%3}, {%4,%5,%6,%7}, {%8,%9}, {%0,%1,%2,%3};"
        : "+f"(d[0]), "+f"(d[1]), "+f"(d[2]), "+f"(d[3]) : "r"(a0), "r"(a1), "r"(a2), "r"(a3), "r"(b0), "r"(b1));
}
__device__ __forceinline__ void mma1688(float* d, uint32_t a0, uint32_t a1, uint32_t b0) {
    asm("mma.sync.aligned.m16n8k8.row.col.f32.bf16.bf16.f32 {%0,%1,%2,%3}, {%4,%5}, {%6}, {%0,%1,%2,%3};"
        : "+f"(d[0]), "+f"(d[1]), "+f"(d[2]), "+f"(d[3]) : "r"(a0), "r"(a1), "r"(b0));
}
__device__ __forceinline__ void ldsm4(uint32_t a, uint32_t* r) {
    asm volatile("ldmatrix.sync.aligned.m8n8.x4.shared.b16 {%0,%1,%2,%3}, [%4];" : "=r"(r[0]), "=r"(r[1]), "=r"(r[2]), "=r"(r[3]) : "r"(a));
}
__device__ __forceinline__ void ldsm4t(uint32_t a, uint32_t* r) {
    asm volatile("ldmatrix.sync.aligned.m8n8.x4.trans.shared.b16 {%0,%1,%2,%3}, [%4];" : "=r"(r[0]), "=r"(r[1]), "=r"(r[2]), "=r"(r[3]) : "r"(a));
}
__device__ __forceinline__ uint32_t nz(uint32_t v) { uint32_t r; asm("max.u32 %0, %1, 1;" : "=r"(r) : "r"(v)); return r; }
__device__ __forceinline__ float rcp(float x) { float r; asm("rcp.approx.ftz.f32 %0, %1;" : "=f"(r) : "f"(x)); return r; }
__device__ __forceinline__ uint2 ld_relaxed2(const void* p) { uint2 v; asm volatile("ld.relaxed.gpu.global.v2.u32 {%0,%1}, [%2];" : "=r"(v.x), "=r"(v.y) : "l"(p) : "memory"); return v; }
__host__ __device__ constexpr uint64_t dconst(uint32_t lbo, uint32_t sbo, uint32_t swz) {
    return ((uint64_t)(lbo >> 4) << 16) | ((uint64_t)(sbo >> 4) << 32) | ((uint64_t)swz << 62);
}
__device__ __forceinline__ uint32_t mkdesc(uint32_t addr, uint64_t c) { return (uint32_t)c | ((addr & 0x3FFFF) >> 4); }
#define WG_FENCE() asm volatile("wgmma.fence.sync.aligned;" ::: "memory")
#define WG_COMMIT() asm volatile("wgmma.commit_group.sync.aligned;" ::: "memory")
#define WG_WAIT(n) asm volatile("wgmma.wait_group.sync.aligned %0;" ::"n"(n) : "memory")
template <int N> __device__ __forceinline__ void reg_fence(float* d) {
#pragma unroll
    for (int i = 0; i < N; i++) asm volatile("" : "+f"(d[i])::"memory");
}
template <int N> __device__ __forceinline__ void reg_def(float* d) {
#pragma unroll
    for (int i = 0; i < N; i++) asm volatile("" : "=f"(d[i]));
}
template <int N> __device__ __forceinline__ void reg_def(uint32_t* d) {
#pragma unroll
    for (int i = 0; i < N; i++) asm volatile("" : "=r"(d[i]));
}
__device__ __forceinline__ void wait_flags(const uint32_t* p, uint32_t target, uint32_t mask) {
    int n = 0;
    while (~__ballot_sync(~0u, ld_relaxed(p) == target) & mask) { if (++n > SPIN_LIMIT) __trap(); }
    asm volatile("fence.acquire.gpu;" ::: "memory");
}
__device__ __forceinline__ float silu_bf(uint32_t cbits) {
    const float c = __uint_as_float(cbits << 16);
    return bf_round(__fdividef(c, 1.f + fminf(ex2(-1.4426950408889634f * c), 1e30f)));
}
__device__ __forceinline__ void gemv_part(uint32_t wmbuf, int wp, int lane) {
    const uint32_t wa = wmbuf + wp * 512 + (8 * (lane >> 4) + (lane & 7)) * 32 + ((lane >> 3) & 1) * 16;
    float d[4] = {};
#pragma unroll
    for (int i = 0; i < 4; i++) {
        uint32_t A[4];
        const float2 v = lds2f(wmbuf + 28672 + (wp + 8 * i) * 32 + (lane & 3) * 8);
        ldsm4t(wa + (i < 3 || wp < 4 ? i : 0) * 4096, A);
        mma16816(d, A[0], A[1], A[2], A[3], __float_as_uint(v.x), __float_as_uint(v.y));
    }
    if ((lane & 3) == 0) {
        sts1(wmbuf + 29696 + (wp * 16 + (lane >> 2)) * 4, __float_as_uint(d[0]));
        sts1(wmbuf + 29696 + (wp * 16 + 8 + (lane >> 2)) * 4, __float_as_uint(d[2]));
    }
}
__device__ __forceinline__ uint32_t mod_word(float v, int col, uint32_t target) {
    v = bf_round(v);
    if ((col >= DM && col < 2 * DM) || (col >= 4 * DM && col < 5 * DM)) v += 1.f;
    return (pack2(v, 0.f) << 16) | (target & 0xFFFFu);
}
__device__ __forceinline__ const uint4* mod_src(int i, int r, int j, bool p2) {
    i = min(i, p2 ? 251 : 223);
    return (const uint4*)g_mod + (r & 7) * (6 * DM / 4) + (i < 224 ? (p2 ? 336 : 0) + i : (i < 238 ? 14 * j + i : 14 * j + i + 322));
}
__device__ __forceinline__ void mod_store(uint32_t sb, uint4 v, const uint4* src, int i) {
    const uint32_t tag = lds1(sb + M_EPOCH) + 1;
    while (__any_sync(~0u, (((v.x ^ tag) | (v.y ^ tag) | (v.z ^ tag) | (v.w ^ tag)) & 0xFFFFu) != 0u)) v = ld_relaxed4(src);
    if (i < 224) {
        const int isc = i >= 112, c4 = i - 112 * isc;
        const uint32_t a = sb + M_ST + (c4 >> 2) * 64 + (c4 & 1) * 32 + (c4 & 2) * 4 + (isc ? 0 : 4);
        sts1(a, __byte_perm(v.x, v.y, 0x7632));
        sts1(a + 16, __byte_perm(v.z, v.w, 0x7632));
    } else if (i < 252) {
        sts4(sb + M_G + (i - 224) * 16, make_uint4(v.x & 0xFFFF0000u, v.y & 0xFFFF0000u, v.z & 0xFFFF0000u, v.w & 0xFFFF0000u));
    }
}
__device__ __forceinline__ int pass_f(int fs, int ps) { return 224 * fs + ((fs & 1) ? (ps == 0 ? 96 : ps == 1 ? 32 : 0) : (ps == 0 ? 0 : ps == 1 ? 128 : 192)); }
__device__ __forceinline__ constexpr uint32_t slot_off(int l) { return l * 16384; }
__device__ __forceinline__ constexpr int g1_slot(int s) { return s % 7; }
__device__ __noinline__ void x1_fix(const uint32_t* g, uint32_t sa, int s) {
#pragma unroll 1
    for (int k = 4 * s; k < 4 * s + 4;) {
        const uint4 v = ld_relaxed4((const uint4*)(g + k * 256));
        sts4(sa + k * 1024, v);
        k += 2 * __all_sync(~0u, min(min(v.x, v.y), min(v.z, v.w)) != 0u);
    }
    __syncwarp();
}
struct LnRow { uint32_t nm, hi, lo; };
__device__ __forceinline__ LnRow ln_coeffs(float mean, float msq) {
    const float var = bf_round(fmaxf(msq - mean * mean, 0.f));
    float sd;
    asm("sqrt.approx.f32 %0, %1;" : "=f"(sd) : "f"(bf_round(var + 1e-5f)));
    const float inv = rcp(bf_round(sd)), hi = bf_round(inv);
    LnRow c;
    c.nm = pack2(-bf_round(mean) * hi, -bf_round(mean) * hi);
    c.hi = pack2(hi, hi);
    c.lo = pack2(inv - hi, inv - hi);
    return c;
}
__device__ __forceinline__ uint32_t ln_norm(uint32_t x, const LnRow& c) {
    return hfma2(x, c.hi, c.nm);
}
__device__ __forceinline__ uint32_t ln_mod(uint32_t y, uint32_t sc, uint32_t sh) {
    return hfma2(y, sc, sh);
}

#define LOADW bulk_e(dst, g_wd + (size_t)((f >> 5) * 4 + nq) * 1792, 7168, bar);
template <int sec> __device__ __forceinline__ void ring_loader(const Params& p, uint32_t sb_, int r_, int j_, int lane) {
    const uint32_t sb = opaque(sb_);
    const int r = opaque(r_), j = opaque(j_), nq = j >> 1, fs = 4 * (j & 1) + nq;
    const int fa = pass_f(fs, 0), fb = pass_f(fs, 1), fc = pass_f(fs, 2);
    const uint32_t* h2src = (const uint32_t*)__shfl_sync(~0u, (unsigned long long)(p.actb + (size_t)r * RB_WORDS + RB_H2), 0);
    const CUtensorMap* gmap = (const CUtensorMap*)__shfl_sync(~0u, (unsigned long long)(&p.ga + sec), 0);
#define BAR(i) (sb + M_BAR + 8 * (i))
#define kh (j & 1)
            int sl = 0;
#pragma unroll 1
            for (int s = 0; s < 28; s++) {
                if (s == 7) { wait_flags(g_flag + (8 * r + j) * 128 + 96 + lane, lds1(sb + M_EPOCH) + 1, 0xFFFFu); fence_async_global(); }
                const int ps = s < 14 ? 0 : s < 21 ? 1 : 2;
                const uint32_t half = ps < 2 ? 8192 : 4096;
                const int sp = sl;
                if (s >= 1 && s < 6) mbar_wait(BAR(B_FULL + s - 1), 0);
                mbar_wait(BAR(B_EMPTY + sp), (s >= 7 && s < 14) || s >= 21);
                expect_e(BAR(B_FULL + sp), half);
                tma3_e(sb + slot_off(sp) + sec * half, gmap + 2 * ps, 0, ps ? 64 * sl : 32 * s, ps == 0 ? fa >> 6 : ps == 1 ? fb >> 6 : fc >> 5, BAR(B_FULL + sp));
                sl = sl == 6 ? 0 : sl + 1;
            }
            if (!sec) PROFH(3);
#pragma unroll 1
            for (int e = 0; e < 4; e++) {
                const uint32_t dst = sb + slot_off(e) + sec * 8192, bar = BAR(B_FULL + e);
                const int f = (e < 2 ? fa + 64 * e : e == 2 ? fb : fc) + 32 * sec;
                mbar_wait(BAR(B_EMPTY + e), 0);
                expect_e(bar, e == 3 && sec ? 0 : 7168);
                if (!(e == 3 && sec)) { LOADW }
            }
            sl = 4;
            int e = 4;
#pragma unroll 1
            for (int grp = 0; grp < 9; grp++) {
                const int ps = grp >= 6 ? 2 : grp >= 3 ? 1 : 0;
                int sidx = grp - 3 * ps;
                if (sec && sidx == 0) { mbar_wait(BAR(B_HRDY + ps), 0); fence_async_global(); }
                sidx += sidx >= nq;
                int f = pass_f(4 * kh + sidx, ps);
#pragma unroll 1
                for (int k = 4 >> ps; k > 0; k--, e++, f += 32) {
                    const uint32_t dst = sb + slot_off(sl), bar = BAR(B_FULL + sl);
                    mbar_wait(BAR(B_EMPTY + sl), e >= 12 && e < 24);
                    if (e >= WIN) mbar_wait(BAR(B_FULL + (sl >= WIN ? sl - WIN : sl + 12 - WIN)), e - WIN >= 12);
                    expect_e(bar, sec ? 8192 : 7168);
                    if (!sec) { LOADW }
                    else bulk_e(dst + 8192, h2src + f * 64, 8192, bar);
                    sl = sl == 11 ? 0 : sl + 1;
                }
            }
            if (!sec) PROFH(4);
}

#define PROF_PARAMS
#define PROF_ARGS
__device__ __noinline__ void helper_late(const Params& p, int r_, int j_, int warp_ PROF_PARAMS) {
    extern __shared__ __align__(1024) unsigned char smem[];
    const uint32_t sb = (uint32_t)__cvta_generic_to_shared(smem);
    const int r = opaque(r_), j = opaque(j_), warp = opaque(warp_), nq = j >> 1, b = 8 * r + j;
    uint32_t* const act = (uint32_t*)__shfl_sync(~0u, (unsigned long long)(p.actb + (size_t)r * RB_WORDS), 0);
    {
        const int lane = fresh_tid() & 31;
        const uint32_t target = lds1(sb + M_EPOCH) + 1;
        if (warp == 8) { expect_e(BAR(B_XCH), 14336); expect_e(BAR(B_XCH + 1), 14336); }
            if (warp == 9) {
#pragma unroll 1
                for (int kv = 0; kv < 2; kv++) {
                    mbar_wait(BAR(B_PUB + kv), 0);
                    wait_flags(g_flag + b * 128 + lane, target, (r >= 2 ? 6u : r == 1 ? 2u : 0u) << (8 * kv));
                    fence_async_global();
                    const uint32_t dst = sb + OFF_Y + (kv ? Y_VR : Y_K);
                    expect_e(BAR(B_KRFULL + kv), r >= 2 ? 28672 : r == 1 ? 14336 : 0);
                    if (r >= 2) bulk_e(dst, act - 2 * RB_WORDS + RB_KV + j * 7168 + kv * 3584, 14336, BAR(B_KRFULL + kv));
                    if (r >= 1) bulk_e(dst + 14336, act - RB_WORDS + RB_KV + j * 7168 + kv * 3584, 14336, BAR(B_KRFULL + kv));
                    if (kv == 0) { PROFH(8); }
                }
            } else if (warp == 8) {
                uint4 v[8];
                mbar_wait(BAR(B_WOFULL), 0);
#pragma unroll
                for (int k = 0; k < 8; k++) v[k] = ld_relaxed4(mod_src(lane + 32 * k, r, j, true));
#pragma unroll
                for (int k = 0; k < 8; k++) mod_store(sb, v[k], mod_src(lane + 32 * k, r, j, true), lane + 32 * k);
                warp_arrive(BAR(B_MOD1));
            } else if (warp == 11) {
                if (kh == 1 && r < 14) {
                    const uint32_t wmbuf = sb + OFF_X + HALF;
                    const int mcol = 2 * DM + 32 * (4 * r + nq);
                    mbar_wait(BAR(B_XFREE), 0);
                    tma3_e(wmbuf, &p.wm2, mcol, 0, 0, BAR(B_WMFULL));
                    tma3_e(wmbuf + 14336, &p.wm2, mcol, 224, 0, BAR(B_WMFULL));
#pragma unroll 1
                    for (int wd = lane; wd < 224; wd += 32) {
                        const uint32_t cb = __ldg((const uint32_t*)p.c + wd);
                        sts1(wmbuf + 28672 + (wd >> 3) * 32 + (wd & 3) * 8 + (wd & 4), pack2(silu_bf(cb & 0xFFFFu), silu_bf(cb >> 16)));
                    }
                    __syncwarp();
                    mbar_wait(BAR(B_WMFULL), 0);
                    const uint32_t wa = wmbuf + (8 * (lane >> 4) + (lane & 7)) * 64 + ((lane >> 3) & 1) * 16;
                    float d[2][4] = {};
#pragma unroll 4
                    for (int ks = 0; ks < 28; ks++) {
                        uint32_t A[8];
                        ldsm4t(wa + ks * 1024, A); ldsm4t(wa + ks * 1024 + 32, A + 4);
                        const float2 v = lds2f(wmbuf + 28672 + ks * 32 + (lane & 3) * 8);
                        mma16816(d[0], A[0], A[1], A[2], A[3], __float_as_uint(v.x), __float_as_uint(v.y));
                        mma16816(d[1], A[4], A[5], A[6], A[7], __float_as_uint(v.x), __float_as_uint(v.y));
                    }
                    const int q = lane & 3, col = mcol + 8 * q + (lane >> 2);
                    const uint32_t word = mod_word(q == 0 ? d[0][0] : q == 1 ? d[0][2] : q == 2 ? d[1][0] : d[1][2], col, target);
#pragma unroll
                    for (int i = 0; i < 8; i++) st_relaxed(g_mod + i * 6 * DM + col, word);
                }
                warp_arrive(BAR(B_WMFREE));
                mbar_wait(BAR(B_VRFULL), 0);
                l2_prefetch_e((const char*)p.wg + (size_t)b * 12544, 12544);
                l2_prefetch_e((const char*)p.wu + (size_t)b * 12544, 12544);
#pragma unroll 1
                for (int k = 0; k < (r < 12 ? 2 : 1); k++) {
                    const int u = 28 * kh + r + 16 * k;
                    expect_e(BAR(B_XFULL + k), 7168);
                    tma3_e(sb + OFF_Y + 102400, &p.dn, 0, 32 * u, 7 * j, BAR(B_XFULL + k));
                    tma3_e(sb + OFF_Y + 102400 + 3584, &p.dn, 0, 32 * u, 7 * (j ^ 1), BAR(B_XFULL + k));
                    mbar_wait(BAR(B_XFULL + k), 1);
                    asm volatile("{\n.reg .pred p;\nelect.sync _|p, 0xffffffff;\n@p cp.async.bulk.global.shared::cta.bulk_group [%0], [%1], 7168;\n"
                                 "cp.async.bulk.commit_group;\ncp.async.bulk.wait_group 0;\n}" ::"l"(g_wd + (size_t)(u * 4 + nq) * 1792), "r"(sb + OFF_Y + 102400) : "memory");
                    __syncwarp();
                }
                warp_arrive(BAR(B_FULLK));
                fence_gpu();
                if (lane < 16) st_relaxed(g_flag + (8 * lane + j) * 128 + 96 + r, target);
            }
        if (warp == 8 || warp == 11) {
            const int sec = warp == 11;
            if (sec) ring_loader<1>(p, sb, r, j, lane); else ring_loader<0>(p, sb, r, j, lane);
            mbar_wait(BAR(B_DONE), 0);
        } else if (warp == 9) {
#pragma unroll
            for (int ev = 0; ev < 4; ev++) { expect_e(BAR(B_GFULL + ev), ev < 2 ? HALF / 2 : 16384); expect_e(BAR(B_XFULL + 2 + ev), ev < 2 ? HALF / 2 : HALF - 16384); }
            mbar_wait(BAR(B_PUB + 2), 0);
            expect_e(BAR(B_FULLV), 4096); expect_e(BAR(B_FULLQ), 4096);
            const uint32_t* fp = g_flag + b * 128 + 32 + lane;
            const int par = (target - 1) & 1;
#pragma unroll 1
            for (int n = 0, ev = 0; ev < 4; n++) {
                if (ev == 1) mbar_wait(BAR(B_PUB + 3), 0);
                uint32_t ok = __ballot_sync(~0u, ld_relaxed(fp) == target) >> (8 * ev);
                while ((ok & 0xFFu) == 0xFFu) {
                    if (ev == 1) mbar_wait(BAR(B_FULLK), 1);
                    asm volatile("fence.acquire.gpu;" ::: "memory");
                    fence_async_global();
                    const int tile = (ev & 1) + (ev >> 1) * par * 2;
                    const uint32_t dst = sb + (ev == 0 ? OFF_X : OFF_Y + (ev & 1) * HALF), first = ev < 2 ? HALF / 2 : 16384;
                    const char* src = (const char*)(act + RB_O + ((ev >> 1) * 2 + tile) * 14336);
                    if (ev >= 2) bulk_e(sb + OFF_X + X_STAT + (ev & 1) * 49152, act + RB_ST + tile * 1024, 4096, BAR(B_FULLV + (ev & 1)));
                    bulk_e(dst, src, first, BAR(B_GFULL + ev));
                    bulk_e(dst + first, src + first, HALF - first, BAR(B_XFULL + 2 + ev));
                    if (ev) PROFH(4 + ev);
                    ev++; ok >>= 8;
                }
                if (n > SPIN_LIMIT) __trap();
            }
            mbar_wait(BAR(B_XFULL + 5), 1);
#pragma unroll 1
            for (int hf = 0; hf < 2; hf++) {
                const int tile = (par ^ 1) * 2 + hf;
                uint4* xz = (uint4*)(act + RB_X1 + tile * 14336 + j * 1792) + lane;
#pragma unroll
                for (int i = 0; i < 14; i++) xz[i * 32] = make_uint4(0, 0, 0, 0);
                ((uint4*)(act + RB_ST + (tile * 8 + j) * 128))[lane] = make_uint4(0, 0, 0, 0);
            }
#pragma unroll 1
            for (int ps = 0; ps < 3; ps++) {
                mbar_wait(BAR(B_PUB + 6 + ps), 0);
                wait_flags(g_flag + b * 128 + 64 + lane, target, (0x55u << kh) << (8 * ps));
                warp_arrive(BAR(B_HRDY + ps));
                PROFH(9 + ps);
            }
        } else {
#pragma unroll 1
            for (int k = 0; k < 9; k++) {
                uint32_t* fp = k < 2 ? g_flag + (b + 8 * lane) * 128 + k * 8 + lane : g_flag + (8 * r + lane) * 128 + 16 + k * 8 + j;
                mbar_wait(BAR(B_PUB + k), 0);
                if (k != 4 && k != 5) fence_gpu();
                if (k < 2 ? (lane == 1 || lane == 2) : lane < 8) st_relaxed(fp, target);
                if (k >= 3 && k <= 5) PROFH(k - 3);
            }
        }
    }
}

__global__ void __cluster_dims__(2, 1, 1) __launch_bounds__(384, 1) fused_block_kernel(const __grid_constant__ Params p) {
    extern __shared__ __align__(1024) unsigned char smem[];
    const uint32_t sb = (uint32_t)__cvta_generic_to_shared(smem);
    const int tid = threadIdx.x, lane = tid & 31, warp = __shfl_sync(~0u, tid >> 5, 0);
    const int m = blockIdx.x >> 1;
    int r, nq;
    if (m < 4) { r = 15; nq = m; }
    else if (m < 36) { r = (m - 4) & 7; nq = (m - 4) >> 3; }
    else { nq = (m - 36) / 7; r = m - 28 - 7 * nq; }
    const int j = opaque(2 * nq + (blockIdx.x & 1)), b = 8 * r + j, fs = 4 * kh + nq;
#define act (p.actb + (size_t)r * RB_WORDS)
    if (lane == 0 && warp < 9 && warp != 6 && warp != 7) {
        const int i0 = warp == 8 ? 0 : 8 + 8 * warp, cnt = warp == 0 || warp == 8 ? 1 : warp < 3 ? 2 : 8;
#pragma unroll
        for (int k = 0; k < 8; k++) if (i0 + k != B_WMFULL) mbar_init(BAR(i0 + k), cnt);
        if (warp == 8) mbar_init(BAR(B_WMFULL), 1);
        asm volatile("fence.mbarrier_init.release.cluster;" ::: "memory");
        fence_async_smem();
    }

    if (warp >= 8) {
        const int lane = fresh_tid() & 31;
        const bool early = kh == 0, gemv = r < 14;
        const int mcol = early ? 16 * (4 * r + nq) : 2 * DM + 32 * (4 * r + nq);
        const uint32_t wmbuf = sb + OFF_Y + HALF;
        if (warp == 8) {
            __syncwarp();
            expect_e(BAR(B_WMFULL), gemv ? 28672 >> early : 0);
            if (early && gemv) { tma3_e(wmbuf, &p.wm, mcol, 0, 0, BAR(B_WMFULL)); tma3_e(wmbuf + 7168, &p.wm, mcol, 224, 0, BAR(B_WMFULL)); }
#pragma unroll
            for (int kb = 0; kb < 7; kb++) {
                expect_e(BAR(B_XFULL + kb), 16384);
                tma3_e(sb + OFF_X + kb * 16384, &p.xm, 64 * kb, 128 * r, 0, BAR(B_XFULL + kb));
            }
        }
        asm volatile("setmaxnreg.dec.sync.aligned.u32 56;");
        if (warp == 9) {
#pragma unroll
            for (int i = 56; i < 64; i++) init_e(BAR(i), 1);
            fence_async_smem();
        }
        bar_arrive(0, 384);
        asm volatile("barrier.cluster.arrive.relaxed.aligned;" ::: "memory");
        if (warp == 8) {
            mbar_wait(BAR(B_XFULL), 0);
            l2_prefetch_e((const char*)p.wqkv + (size_t)b * 9408, 9408);
#pragma unroll 1
            for (int mt = 0; mt < 4; mt++) {
                if (mt == 1) bar_sync(9, 384);
                if (mt == 3) mbar_wait(BAR(B_WMFREE), 0);
                if (mt == 1 && early) mbar_wait(BAR(B_WMFREE), 0);
                if (mt) mbar_wait(BAR(mt == 1 ? B_FULLK : mt == 2 ? B_MOD1 : B_VRFULL), 0);
                const uint32_t bar = BAR(mt == 3 ? B_WOFULL : B_FULLK + mt), dst = sb + (mt < 2 ? OFF_Y : OFF_X) + (mt & 1) * HALF;
                const int c0 = (mt < 2 ? DM + DM * mt : 0) + 56 * j - 8 * kh;
                expect_e(bar, HALF);
                tma3_e(dst, mt == 3 ? &p.wo : &p.qkv, c0, 0, 0, bar);
                tma3_e(dst + HALF / 2, mt == 3 ? &p.wo : &p.qkv, c0, 224, 0, bar);
            }
        } else {
            bar_sync(9, 384);
            if (warp == 11 && early) {
                const uint32_t target = lds1(sb + M_EPOCH) + 1;
                mbar_wait(BAR(B_GEMV), 0);
                float sum = 0.f;
#pragma unroll
                for (int i = 0; i < 8; i++) sum += *(const float*)(smem + OFF_Y + HALF + 29696 + (i * 16 + (lane & 15)) * 4);
                uint32_t* mg = g_mod + mcol + (lane & 15) + (lane >> 4) * 4 * 6 * DM;
                const uint32_t word = mod_word(sum, mcol, target);
                if (gemv) { st_relaxed(mg, word); st_relaxed(mg + 6 * DM, word); st_relaxed(mg + 12 * DM, word); st_relaxed(mg + 18 * DM, word); }
            }
        }
    }
    if (warp < 8) {
        const int w = (warp >> 2) ^ 1, wi = warp & 3;
#define COORDS const int t = fresh_tid() & 127, lane = t & 31, q = lane & 3, lr = lane >> 2, ra = 64 * w + 16 * wi + lr; \
        const uint32_t lx = (lane >> 4) ^ (lane & 7), mrow = (64 * w + 16 * wi + ((lane >> 3) & 1) * 8 + (lane & 7)) * 128; \
        (void)q; (void)lr; (void)ra; (void)lx; (void)mrow;
#define WAIT(i, par) mbar_wait_c(BAR(i), par)
        constexpr uint64_t DB128 = dconst(4096, 1024, 1);
        {
            const int wd = fresh_tid();
            const uint32_t cb = wd < 224 ? __ldg((const uint32_t*)p.c + wd) : 0u;
            if (wd == 255) sts1(sb + M_EPOCH, atomicAdd(&g_ticket, 1u) / NCTA);
            sts1(sb + OFF_Y + HALF + 28672 + (wd >> 3) * 32 + (wd & 3) * 8 + (wd & 4), pack2(silu_bf(cb & 0xFFFFu), silu_bf(cb >> 16)));
        }
        bar_arrive(9, 384);
        bar_sync(0, 384);
        asm volatile("barrier.cluster.arrive.relaxed.aligned;" ::: "memory");
        asm volatile("setmaxnreg.inc.sync.aligned.u32 224;");
        PROFC(0);
        uint32_t xr[16];
        {
            COORDS
            uint32_t h[112];
            LnRow ca, cb;
            const int mi = min(128 * w + t, 223);
            const uint4* msrc = mod_src(mi, r, j, false);
            uint4 mv;
            {
                float ds[4] = {}, da[2][4] = {}, db[2][4] = {};
                const uint32_t ONE2 = 0x3F803F80u;
#pragma unroll
                for (int kb = 0; kb < 7; kb++) {
                    if (kb == 0 && kh == 0) { WAIT(B_WMFULL, 0); gemv_part(sb + OFF_Y + HALF, warp, lane); warp_arrive(BAR(B_GEMV)); }
                    WAIT(B_XFULL + kb, 0);
#pragma unroll
                    for (int k4 = 0; k4 < 4; k4++) ldsm4(sb + OFF_X + mrow + kb * 16384 + (((2 * k4) ^ lx) << 4), h + 16 * kb + 4 * k4);
#pragma unroll
                    for (int k4 = 0; k4 < 4; k4++) {
                        const uint32_t* f = h + 16 * kb + 4 * k4;
                        mma16816(ds, f[0], f[1], f[2], f[3], ONE2, ONE2);
                        mma1688(da[0], f[0], f[1], f[0]); mma1688(db[0], f[0], f[1], f[1]);
                        mma1688(da[1], f[2], f[3], f[2]); mma1688(db[1], f[2], f[3], f[3]);
                    }
                }
#pragma unroll
                for (int i = 0; i < 4; i++) {
                    const int ch = 7 * j + 2 * i + (lane >> 4);
                    ldsm4(sb + OFF_X + mrow + (ch >> 3) * 16384 + (((ch ^ lane) & 7) << 4), xr + 4 * i);
                }
                mv = ld_relaxed4(msrc);
                warp_arrive(BAR(B_XFREE));
                float qa = (lr & 1) ? da[0][1] + da[1][1] : da[0][0] + da[1][0];
                float qb = (lr & 1) ? db[0][3] + db[1][3] : db[0][2] + db[1][2];
                const int src = (lane & ~3) | (lr >> 1);
                qa = __shfl_sync(~0u, qa, src);
                qb = __shfl_sync(~0u, qb, src);
                ca = ln_coeffs(ds[0] * (1.f / DM), qa * (1.f / DM));
                cb = ln_coeffs(ds[2] * (1.f / DM), qb * (1.f / DM));
#pragma unroll
                for (int i = 0; i < 4 * NPRE; i += 2) { h[i] = ln_norm(h[i], ca); h[i + 1] = ln_norm(h[i + 1], cb); }
            }
            PROFC(1);
            {
                float ak[28], av[28], aq[28];
                uint32_t kp[14], vp[14];
                const uint64_t bq0 = (DB128 & ~0xFFFFFFFFull) | (mkdesc(sb + OFF_X, DB128) + kh), bk0 = bq0 + (OFF_Y >> 4), bv0 = bk0 + (HALF >> 4);
                uint32_t* kvg = act + RB_KV + j * 7168 + (8 * w + 2 * wi) * 224 + lane;
                mod_store(sb, mv, msrc, mi);
                bar_sync(3, 256);
                if (warp == 0) warp_arrive(BAR(B_MOD1));
                WAIT(B_FULLK, 0);
                PROFC(2);
                reg_def<28>(ak);
#pragma unroll
                for (int g4 = 0; g4 < 4; g4++) {
#pragma unroll
                    for (int ks = 7 * g4; ks < 7 * g4 + 7; ks++) {
                        const uint4 st = *(const uint4*)(smem + M_ST + ks * 64 + q * 16);
                        if (ks >= NPRE) {
                            h[4 * ks] = ln_norm(h[4 * ks], ca); h[4 * ks + 1] = ln_norm(h[4 * ks + 1], cb);
                            h[4 * ks + 2] = ln_norm(h[4 * ks + 2], ca); h[4 * ks + 3] = ln_norm(h[4 * ks + 3], cb);
                        }
                        h[4 * ks] = ln_mod(h[4 * ks], st.x, st.y); h[4 * ks + 1] = ln_mod(h[4 * ks + 1], st.x, st.y);
                        h[4 * ks + 2] = ln_mod(h[4 * ks + 2], st.z, st.w); h[4 * ks + 3] = ln_mod(h[4 * ks + 3], st.z, st.w);
                    }
                    WG_FENCE();
#pragma unroll
                    for (int ks = 7 * g4; ks < 7 * g4 + 7; ks++) wgmma_rl_56(ak, h[4 * ks], h[4 * ks + 1], h[4 * ks + 2], h[4 * ks + 3], bk0 + ks * 128, ks != 0);
                }
                WG_COMMIT();
                PROFC(3);
                reg_def<28>(av);
                WG_WAIT(0);
                reg_fence<28>(ak);
#pragma unroll
                for (int g = 0; g < 7; g++) {
                    kp[2 * g] = pack2(ak[4 * g], ak[4 * g + 1]); kp[2 * g + 1] = pack2(ak[4 * g + 2], ak[4 * g + 3]);
                    kvg[g * 32] = kp[2 * g]; kvg[224 + g * 32] = kp[2 * g + 1];
                }
                warp_arrive(BAR(B_PUB));
                PROFC(4);
                WAIT(B_FULLV, 0);
                WG_FENCE();
#pragma unroll
                for (int ks = 0; ks < 28; ks++) wgmma_rl_56(av, h[4 * ks], h[4 * ks + 1], h[4 * ks + 2], h[4 * ks + 3], bv0 + ks * 128, ks != 0);
                WG_COMMIT();
                reg_def<28>(aq);
                WAIT(B_FULLQ, 0);
                WG_FENCE();
#pragma unroll
                for (int ks = 0; ks < VPRE; ks++) wgmma_rl_56(aq, h[4 * ks], h[4 * ks + 1], h[4 * ks + 2], h[4 * ks + 3], bq0 + ks * 128, ks != 0);
                WG_COMMIT();
                WG_WAIT(1);
                reg_fence<28>(av);
#pragma unroll
                for (int g = 0; g < 7; g++) {
                    vp[2 * g] = pack2(av[4 * g], av[4 * g + 1]); vp[2 * g + 1] = pack2(av[4 * g + 2], av[4 * g + 3]);
                    kvg[3584 + g * 32] = vp[2 * g]; kvg[3584 + 224 + g * 32] = vp[2 * g + 1];
                }
                warp_arrive(BAR(B_PUB + 1));
                PROFC(5);
                WG_FENCE();
#pragma unroll
                for (int ks = VPRE; ks < 28; ks++) wgmma_rl_56(aq, h[4 * ks], h[4 * ks + 1], h[4 * ks + 2], h[4 * ks + 3], bq0 + ks * 128, ks != 0);
                WG_COMMIT();
                WAIT(B_PUB + 1, 0);
                const uint32_t rg = 8 * w + 2 * wi + ((lane >> 3) & 1);
                const uint32_t ko = sb + OFF_Y + Y_KOWN + rg * 896 + (lane & 7) * 16, qo = sb + OFF_Y + Y_Q + rg * 1024 + (lane >> 4) * 128 + (lane & 7) * 16;
#pragma unroll
                for (int g = 0; g < 6; g += 2) {
                    stsm4(ko + (g + (lane >> 4)) * 128, kp[2 * g], kp[2 * g + 1], kp[2 * g + 2], kp[2 * g + 3]);
                    stsm4(ko + (Y_VOWN - Y_KOWN) + (g + (lane >> 4)) * 128, vp[2 * g], vp[2 * g + 1], vp[2 * g + 2], vp[2 * g + 3]);
                }
                stsm4(ko + (lane >> 4) * (Y_VOWN - Y_KOWN) + 6 * 128, kp[12], kp[13], vp[12], vp[13]);
                WG_WAIT(0);
                reg_fence<28>(aq);
                __syncwarp();
                if (lane < 3 && w == 1) mbar_arrive(BAR(B_EMPTY + lane));
                uint32_t qp[14];
#pragma unroll
                for (int i = 0; i < 14; i++) qp[i] = pack2(aq[2 * i], aq[2 * i + 1]);
                stsm4(qo, qp[0], qp[1], qp[2], qp[3]);
                stsm4(qo + 256, qp[4], qp[5], q < 2 ? qp[6] : 0u, q < 2 ? qp[7] : 0u);
                stsm4(qo + 512, q < 2 ? 0u : qp[6], q < 2 ? 0u : qp[7], qp[8], qp[9]);
                stsm4(qo + 768, qp[10], qp[11], qp[12], qp[13]);
                fence_async_smem();
                if (w == 0) { bar_arrive(4, 256); bar_sync(1, 128); } else { bar_arrive(5, 256); bar_sync(4, 256); }
            }
        }
        PROFC(6);
        WAIT(B_KRFULL, 0);
        PROFC(7);
        {
#pragma unroll 1
            for (int hf = 0; hf < 2; hf++) {
                COORDS
                if (hf > w) bar_sync(5, 256);
                float s[160];
                const float CS = 0.18898223650461361f * 1.4426950408889634f;
                const float NEG = __int_as_float(0xFF800000);
                constexpr uint64_t DQ = dconst(128, 1024, 0), DK = dconst(128, 896, 0);
                {
                    const uint32_t qd = mkdesc(sb + OFF_Y + Y_Q + hf * 8192 + w * 512, DQ), kd = mkdesc(sb + OFF_Y + Y_K + hf * 8 * 896 + w * 384, DK);
                    reg_def<160>(s);
                    WG_FENCE();
                    wgmma_sk_160<DQ, DK>(s, qd, kd, 0);
                    wgmma_sk_160<DQ, DK>(s, qd + 16, kd + 16, 1);
                    wgmma_sk_160<DQ, DK>(s + 80, qd, kd + 20 * 56, 0);
                    wgmma_sk_160<DQ, DK>(s + 80, qd + 16, kd + 20 * 56 + 16, 1);
                    WG_COMMIT();
                    WG_WAIT(0);
                    reg_fence<160>(s);
                }
                if (r < 2) {
                    const int pmin = 4 - 2 * r - hf;
#pragma unroll
                    for (int p4 = 0; p4 < 4; p4++)
                        if (p4 < pmin) {
#pragma unroll
                            for (int i = 0; i < 32; i++) asm volatile("mov.b32 %0, 0xFF800000;" : "=f"(s[32 * p4 + i]));
                        }
                }
                const bool c0 = 2 * q > lr, c1 = 2 * q + 1 > lr;
#pragma unroll
                for (int pp = 0; pp < 4; pp++) {
                    const bool me = pp == wi;
                    float* e = s + 8 * pp;
                    if (me && !c0) { e[0] = NEG; e[6] = NEG; }
                    if (me && !c1) { e[1] = NEG; e[7] = NEG; }
                    if (me) { e[2] = NEG; e[3] = NEG; }
                    e = s + 8 * (pp + 16);
                    if (me && c0) { e[0] = NEG; e[6] = NEG; }
                    if (me && c1) { e[1] = NEG; e[7] = NEG; }
                    if (me) { e[4] = NEG; e[5] = NEG; }
                }
#pragma unroll
                for (int i = 0; i < 24; i++) s[i] = (i >> 3) < wi ? s[136 + i] : s[i];
                int i0 = 0x80000000, i1 = 0x80000000, i2 = 0x80000000, i3 = 0x80000000;
#pragma unroll
                for (int pp = 0; pp < 17; pp++) {
                    const float* e = s + 8 * pp;
                    i0 = __vimax3_s32(i0, __float_as_int(e[0]), __float_as_int(e[1])); i1 = __vimax3_s32(i1, __float_as_int(e[2]), __float_as_int(e[3]));
                    i2 = __vimax3_s32(i2, __float_as_int(e[4]), __float_as_int(e[5])); i3 = __vimax3_s32(i3, __float_as_int(e[6]), __float_as_int(e[7]));
                }
                i0 = max(i0, i2); i1 = max(i1, i3);
                i0 = max(i0, __shfl_xor_sync(~0u, i0, 1)); i1 = max(i1, __shfl_xor_sync(~0u, i1, 1));
                i0 = max(i0, __shfl_xor_sync(~0u, i0, 2)); i1 = max(i1, __shfl_xor_sync(~0u, i1, 2));
                if (__any_sync(~0u, (i0 | i1) < 0)) {
                    uint32_t u0 = ~0u, u1 = ~0u, u2 = ~0u, u3 = ~0u;
#pragma unroll
                    for (int pp = 0; pp < 17; pp++) {
                        const float* e = s + 8 * pp;
                        u0 = __vimin3_u32(u0, __float_as_uint(e[0]), __float_as_uint(e[1])); u1 = __vimin3_u32(u1, __float_as_uint(e[2]), __float_as_uint(e[3]));
                        u2 = __vimin3_u32(u2, __float_as_uint(e[4]), __float_as_uint(e[5])); u3 = __vimin3_u32(u3, __float_as_uint(e[6]), __float_as_uint(e[7]));
                    }
                    u0 = min(u0, u2); u1 = min(u1, u3);
                    u0 = min(u0, __shfl_xor_sync(~0u, u0, 1)); u1 = min(u1, __shfl_xor_sync(~0u, u1, 1));
                    u0 = min(u0, __shfl_xor_sync(~0u, u0, 2)); u1 = min(u1, __shfl_xor_sync(~0u, u1, 2));
                    if (i0 < 0) i0 = u0;
                    if (i1 < 0) i1 = u1;
                }
                const float ma = __int_as_float(i0), mb = __int_as_float(i1);
                const float na = -ma * CS, nb = -mb * CS;
                PROFC(8 + 3 * hf);
                {
                    WAIT(B_VRFULL, 0);
                    float o[16] = {}, rs[4] = {};
                    const uint32_t va = sb + OFF_Y + Y_VR + (8 * hf + ((lane >> 3) & 1)) * 896 + (3 * w + (lane >> 4)) * 128 + (lane & 7) * 16;
                    constexpr uint32_t OWN = Y_VOWN - 32 * 896;
#pragma unroll
                    for (int pp = 0; pp < 17; pp++) {
                        uint32_t B[8];
                        const uint32_t v = va + pp * 1792 + (pp < 3 ? (pp < wi ? 17 * 1792 + OWN : 0) : pp == 16 ? OWN : pp >= 12 ? hf * OWN : 0);
                        ldsm4t(v, B); ldsm4t(v + 256, B + 4);
                        float e[8];
#pragma unroll
                        for (int i = 0; i < 8; i++) e[i] = ex2(fmaf(s[8 * pp + i], CS, (i & 2) ? nb : na));
                        const uint32_t p0 = pack2(e[0], e[1]), p1 = pack2(e[2], e[3]), p2 = pack2(e[4], e[5]), p3 = pack2(e[6], e[7]);
                        mma16816(rs, p0, p1, p2, p3, 0x3F803F80u, 0x3F803F80u);
#pragma unroll
                        for (int g = 0; g < 4; g++) mma16816(o + 4 * g, p0, p1, p2, p3, B[2 * g], B[2 * g + 1]);
                    }
                    PROFC(9 + 3 * hf);
                    const float ia = rcp(rs[0]), ib = rcp(rs[2]);
                    uint32_t* og = act + RB_O + hf * 14336 + (7 * j + 3 * w) * 256 + wi * 64 + lane;
#pragma unroll
                    for (int g = 0; g < 4; g++) {
                        if ((g == 3 - 3 * w) ? ((q >> 1) == w) : true) {
                            og[g * 256] = pack2(o[4 * g] * ia, o[4 * g + 1] * ia);
                            og[g * 256 + 32] = pack2(o[4 * g + 2] * ib, o[4 * g + 3] * ib);
                        }
                    }
                    warp_arrive(BAR(B_PUB + 2 + hf));
                    PROFC(10 + 3 * hf);
                }
            }
        }
        uint32_t x1p[14];
        COORDS
        constexpr uint64_t DT = dconst(1024, 128, 0);
        const int tile = opaque((lds1(sb + M_EPOCH) & 1) * 2 + w);
        {
            float ac[28];
            const uint32_t ad = mkdesc(sb + (w ? OFF_Y + HALF : OFF_X), DT), bd = mkdesc(sb + OFF_X + HALF, DB128) + kh;
            WAIT(B_WOFULL, 0);
            WAIT(B_MOD1, 1);
            WAIT(B_GFULL + w, 0);
            PROFC(28);
            reg_def<28>(ac);
#pragma unroll 1
            for (int u = 0; u < 4; u++) {
                if (u == 2) WAIT(B_XFULL + 2 + w, 1);
                WG_FENCE();
#pragma unroll
                for (int i = 0; i < 7; i++) wgmma_ss_56<DT, DB128>(ac, ad + (7 * u + i) * 128, bd + (7 * u + i) * 128, (u | i) != 0);
            }
            WG_COMMIT();
            WG_WAIT(0);
            reg_fence<28>(ac);
            PROFC(14);
            __syncwarp();
            if (lane < 3) mbar_arrive(BAR(B_EMPTY + 4 - w + lane));
            if (lane < 3 && w == 0) mbar_arrive(BAR(B_EMPTY + lane));
            float ds[4] = {}, da[4] = {}, db[4] = {};
            uint32_t* xo = act + RB_X1 + tile * 14336 + 7 * j * 256 + wi * 64 + lane;
#pragma unroll
            for (int g = 0; g < 7; g++) {
                const float2 ga = *(const float2*)(smem + M_G + (8 * g + 2 * q) * 4);
                x1p[2 * g] = pack2(fmaf(ga.x, ac[4 * g], bf_lo(xr[2 * g])), fmaf(ga.y, ac[4 * g + 1], bf_hi(xr[2 * g])));
                x1p[2 * g + 1] = pack2(fmaf(ga.x, ac[4 * g + 2], bf_lo(xr[2 * g + 1])), fmaf(ga.y, ac[4 * g + 3], bf_hi(xr[2 * g + 1])));
                st_relaxed(xo + g * 256, nz(x1p[2 * g])); st_relaxed(xo + g * 256 + 32, nz(x1p[2 * g + 1]));
                mma1688(ds, x1p[2 * g], x1p[2 * g + 1], 0x3F803F80u);
                mma1688(da, x1p[2 * g], x1p[2 * g + 1], x1p[2 * g]);
                mma1688(db, x1p[2 * g], x1p[2 * g + 1], x1p[2 * g + 1]);
            }
            const int src = (lane & ~3) | (lr >> 1);
            const float qa = __shfl_sync(~0u, (lr & 1) ? da[1] : da[0], src), qb = __shfl_sync(~0u, (lr & 1) ? db[3] : db[2], src);
            const float kk = (q & 1) ? ((q & 2) ? qb : qa) : ((q & 2) ? ds[2] : ds[0]);
            st_relaxed(act + RB_ST + ((tile * 8 + j) * 64 + 16 * wi + lr + 4 * (q & 2)) * 2 + (q & 1), nz(__float_as_uint(kk)));
            __syncwarp();
            if (lane < 2) mbar_arrive(BAR(B_PUB + 4 + w));
        }
        PROFC(15);
        uint32_t h2a[32], h2b[24];
        {
            const int fa = pass_f(fs, 0), fb = pass_f(fs, 1), fc = pass_f(fs, 2);
            uint32_t* h2g = act + RB_H2 + (8 * w + 2 * wi) * 32 + lane;
            const uint32_t a0 = mkdesc(sb + OFF_Y + w * HALF, DT);
            {
                LnRow ca, cb;
                {
                    const uint32_t* sg = act + RB_ST + ((tile * 8 + 2 * q) * 64 + 16 * wi + lr) * 2;
                    uint2 u[4];
                    WAIT(B_FULLV + w, 1);
                    PROFC(16);
#pragma unroll
                    for (int i = 0; i < 4; i++) { const float2 v = lds2f(sb + OFF_X + X_STAT + w * 49152 + ((2 * q + (i >> 1)) * 64 + 16 * wi + lr + 8 * (i & 1)) * 8); u[i] = make_uint2(__float_as_uint(v.x), __float_as_uint(v.y)); }
                    while (__any_sync(~0u, min(min(min(u[0].x, u[0].y), min(u[1].x, u[1].y)), min(min(u[2].x, u[2].y), min(u[3].x, u[3].y))) == 0u)) {
#pragma unroll
                        for (int i = 0; i < 4; i++) u[i] = ld_relaxed2(sg + (i >> 1) * 128 + (i & 1) * 16);
                    }
                    warp_arrive(BAR(B_EMPTY + 3 + 3 * w));
                    float v[4] = {__uint_as_float(u[0].x) + __uint_as_float(u[2].x), __uint_as_float(u[0].y) + __uint_as_float(u[2].y),
                                  __uint_as_float(u[1].x) + __uint_as_float(u[3].x), __uint_as_float(u[1].y) + __uint_as_float(u[3].y)};
#pragma unroll
                    for (int i = 0; i < 4; i++) { v[i] += __shfl_xor_sync(~0u, v[i], 1); v[i] += __shfl_xor_sync(~0u, v[i], 2); }
                    ca = ln_coeffs(v[0] * (1.f / DM), v[1] * (1.f / DM));
                    cb = ln_coeffs(v[2] * (1.f / DM), v[3] * (1.f / DM));
                }
                const uint32_t ha = sb + OFF_Y + w * HALF + (lane >> 4) * 1024 + (2 * wi + ((lane >> 3) & 1)) * 128 + (lane & 7) * 16;
                const uint32_t sta = sb + M_ST + q * 16;
                const uint32_t* xg = act + RB_X1 + tile * 14336 + (lane >> 4) * 256 + wi * 64 + (lane & 15) * 4;
                uint32_t x[8];
                const uint32_t xs = sb + OFF_Y + w * HALF + (lane >> 4) * 1024 + wi * 256 + (lane & 15) * 16;
                uint4 st[2];
                auto load = [&](int s) {
                    if (s == 4) mbar_wait_c(BAR(B_XFULL + 4 + w), 1);
                    ldsm4(ha + s * 4096, x); ldsm4(ha + s * 4096 + 2048, x + 4);
                    st[0] = lds4(sta + s * 128); st[1] = lds4(sta + s * 128 + 64);
                };
                auto prep = [&](int s, uint32_t* f) {
                    if (__any_sync(~0u, min(min(min(x[0], x[1]), min(x[2], x[3])), min(min(x[4], x[5]), min(x[6], x[7]))) == 0u)) {
                        WG_WAIT(0);
                        x1_fix(xg, xs, s);
                        ldsm4(ha + s * 4096, x); ldsm4(ha + s * 4096 + 2048, x + 4);
                    }
#pragma unroll
                    for (int i = 0; i < 2; i++) {
                        f[4 * i] = ln_mod(ln_norm(x[4 * i], ca), st[i].x, st[i].y); f[4 * i + 1] = ln_mod(ln_norm(x[4 * i + 1], cb), st[i].x, st[i].y);
                        f[4 * i + 2] = ln_mod(ln_norm(x[4 * i + 2], ca), st[i].z, st[i].w); f[4 * i + 3] = ln_mod(ln_norm(x[4 * i + 3], cb), st[i].z, st[i].w);
                    }
                    if (s < 13) load(s + 1);
                    stsm4(ha + s * 4096, f[0], f[1], f[2], f[3]); stsm4(ha + s * 4096 + 2048, f[4], f[5], f[6], f[7]);
                };
                float ac[128];
                uint32_t fr[3][8];
                uint64_t bd = (DB128 & ~0xFFFFFFFFull) | mkdesc(sb, DB128);
                reg_def<128>(ac);
                WAIT(B_GFULL + 2 + w, 0);
                load(0);
                prep(0, fr[0]);
                PROFC(17);
#pragma unroll
                for (int s = 0; s < 14; s++) {
                    const uint32_t* f = fr[s % 3];
                    WAIT(B_FULL + g1_slot(s), s >= 7);
                    WG_FENCE();
                    wgmma_rl_256(ac, f[0], f[1], f[2], f[3], bd, s != 0);
                    wgmma_rl_256(ac, f[4], f[5], f[6], f[7], bd + 128, 1);
                    bd += s == 6 ? p.zero - 6 * 1024ull : 1024;
                    WG_COMMIT();
                    if (s < 13) prep(s + 1, fr[(s + 1) % 3]);
                    if (s > 0) { WG_WAIT(1); warp_arrive(BAR(B_EMPTY + g1_slot(s - 1))); }
                }
                fence_async_smem();
                PROFC(18);
                WG_WAIT(0);
                reg_fence<128>(ac);
                warp_arrive(BAR(B_EMPTY + 6));
#pragma unroll
                for (int g = 0; g < 16; g++) {
                    h2a[2 * g] = hmul2(pack2_relu(ac[4 * g], ac[4 * g + 1]), pack2(ac[64 + 4 * g], ac[64 + 4 * g + 1]));
                    h2a[2 * g + 1] = hmul2(pack2_relu(ac[4 * g + 2], ac[4 * g + 3]), pack2(ac[64 + 4 * g + 2], ac[64 + 4 * g + 3]));
                }
                bar_sync(1 + w, 128);
            }
            PROFC(19);
            {
                float ac[64];
                reg_def<64>(ac);
                const uint32_t bx = mkdesc(sb, dconst(8192, 1024, 1));
#pragma unroll 1
                for (int s = 0; s < 7; s++) {
                    WAIT(B_FULL + s, 0);
                    const uint32_t ad = a0 + s * 512, bd = bx + (slot_off(s) >> 4);
                    WG_FENCE();
#pragma unroll
                    for (int k = 0; k < 4; k++) wgmma_ss_128<DT, DB128>(ac, ad + k * 128, bd + k * 128, (s | k) != 0);
                    WG_COMMIT();
                    if (s == 1) {
#pragma unroll
                        for (int g = 0; g < 16; g++) { h2g[(fa / 8 + g) * 512] = h2a[2 * g]; h2g[(fa / 8 + g) * 512 + 32] = h2a[2 * g + 1]; }
                        warp_arrive(BAR(B_PUB + 6));
                    }
                    if (s > 0) { WG_WAIT(1); warp_arrive(BAR(B_EMPTY + s - 1)); }
                }
                WG_WAIT(0);
                reg_fence<64>(ac);
                warp_arrive(BAR(B_EMPTY + 6));
#pragma unroll
                for (int g = 0; g < 8; g++) {
                    h2b[2 * g] = hmul2(pack2_relu(ac[4 * g], ac[4 * g + 1]), pack2(ac[32 + 4 * g], ac[32 + 4 * g + 1]));
                    h2b[2 * g + 1] = hmul2(pack2_relu(ac[4 * g + 2], ac[4 * g + 3]), pack2(ac[32 + 4 * g + 2], ac[32 + 4 * g + 3]));
                }
            }
            PROFC(27);
            {
                float ac[32];
                reg_def<32>(ac);
                const uint32_t bx = mkdesc(sb, dconst(4096, 512, 2));
#pragma unroll 1
                for (int s = 0; s < 7; s++) {
                    WAIT(B_FULL + s, 1);
                    const uint32_t ad = a0 + s * 512, bd = bx + (slot_off(s) >> 4);
                    WG_FENCE();
#pragma unroll
                    for (int k = 0; k < 4; k++) wgmma_ss_64<DT, dconst(4096, 512, 2)>(ac, ad + k * 128, bd + k * 64, (s | k) != 0);
                    WG_COMMIT();
                    if (s == 1) {
#pragma unroll
                        for (int g = 0; g < 8; g++) { h2g[(fb / 8 + g) * 512] = h2b[2 * g]; h2g[(fb / 8 + g) * 512 + 32] = h2b[2 * g + 1]; }
                        warp_arrive(BAR(B_PUB + 7));
                    }
                    if (s > 0) { WG_WAIT(1); warp_arrive(BAR(B_EMPTY + s - 1)); }
                }
                WG_WAIT(0);
                reg_fence<32>(ac);
                __syncwarp();
                if (lane < 6) mbar_arrive(BAR(B_EMPTY + 6 + lane));
                PROFC(20);
#pragma unroll
                for (int g = 0; g < 4; g++) {
                    h2b[16 + 2 * g] = hmul2(pack2_relu(ac[4 * g], ac[4 * g + 1]), pack2(ac[16 + 4 * g], ac[16 + 4 * g + 1]));
                    h2b[16 + 2 * g + 1] = hmul2(pack2_relu(ac[4 * g + 2], ac[4 * g + 3]), pack2(ac[16 + 4 * g + 2], ac[16 + 4 * g + 3]));
                    h2g[(fc / 8 + g) * 512] = h2b[16 + 2 * g]; h2g[(fc / 8 + g) * 512 + 32] = h2b[16 + 2 * g + 1];
                }
                warp_arrive(BAR(B_PUB + 8));
                asm volatile("barrier.cluster.wait.aligned;" ::: "memory");
                if (lane == 0) {
                    uint32_t rb;
                    asm volatile("mapa.shared::cluster.u32 %0, %1, %2;" : "=r"(rb) : "r"(BAR(B_PEER)), "r"(kh ^ 1));
                    asm volatile("mbarrier.arrive.relaxed.cluster.shared::cluster.b64 _, [%0];" ::"r"(rb) : "memory");
                }
            }
        }
        PROFC(21);
        {
            float ac[56];
            reg_def<56>(ac);
            constexpr uint64_t DAN = dconst(2048, 128, 0);
            constexpr uint64_t DW = dconst(128, 512, 0);
            const uint32_t bx = mkdesc(sb, DW);
#pragma unroll
            for (int e = 0; e < 4; e++) {
                WAIT(B_FULL + e, 0);
                const uint64_t bd = ((DW & ~0xFFFFFFFFull) | bx) + (slot_off(e) >> 4);
                const uint32_t* hh = e < 2 ? h2a + 16 * e : h2b + 16 * (e - 2);
                WG_FENCE();
#pragma unroll
                for (int k = 0; k < (e < 3 ? 4 : 2); k++) wgmma_rl_112(ac, hh[4 * k], hh[4 * k + 1], hh[4 * k + 2], hh[4 * k + 3], bd + (k >> 1) * 512 + (k & 1) * 16, (e | k) != 0);
                WG_COMMIT();
                if (e > 0) { WG_WAIT(1); warp_arrive(BAR(B_EMPTY + e - 1)); }
            }
            PROFC(22);
            uint32_t ad = mkdesc(sb + 4 * 16384 + 8192 + w * 1024, DAN), bd = bx + 4 * 1024, fb_ = BAR(B_FULL + 4), eb_ = BAR(B_EMPTY + 3), par = 0;
#pragma unroll 1
            for (int e = 4; e < 25; e++) {
                mbar_wait_c(fb_, par);
                WG_FENCE();
                wgmma_ss_112<DAN, DW>(ac, ad, bd, 1);
                wgmma_ss_112<DAN, DW>(ac, ad + 256, bd + 16, 1);
                WG_COMMIT();
                WG_WAIT(1);
                warp_arrive(eb_);
                eb_ = fb_ + 8 * (B_EMPTY - B_FULL);
                ad += 1024; bd += 1024; fb_ += 8;
                if (e == 11 || e == 23) { ad -= 12 * 1024; bd -= 12 * 1024; fb_ -= 96; par ^= 1; }
            }
            mbar_wait_cluster(BAR(B_PEER), 0);
            WG_WAIT(0);
            reg_fence<56>(ac);
            PROFC(24);
            uint32_t rdst, rbar;
            asm volatile("mapa.shared::cluster.u32 %0, %1, %2;" : "=r"(rdst) : "r"(sb + OFF_Y + (5 + w) * 16384 + t * 16), "r"(kh ^ 1));
            asm volatile("mapa.shared::cluster.u32 %0, %1, %2;" : "=r"(rbar) : "r"(BAR(B_XCH + w)), "r"(kh ^ 1));
#pragma unroll
            for (int g = 0; g < 7; g++) {
                const float v0 = ac[28 + 4 * g + 0], v1 = ac[28 + 4 * g + 1];
                const float v2 = ac[28 + 4 * g + 2], v3 = ac[28 + 4 * g + 3];
                asm volatile("st.async.shared::cluster.mbarrier::complete_tx::bytes.v4.f32 [%0], {%1,%2,%3,%4}, [%5];"
                             ::"r"(rdst + g * 2048), "f"(v0), "f"(v1), "f"(v2), "f"(v3), "r"(rbar) : "memory");
            }
            mbar_wait_cluster(BAR(B_XCH + w), 0);
            PROFC(25);
            uint32_t op[16];
#pragma unroll
            for (int g = 0; g < 7; g++) {
                const uint4 rv = *(const uint4*)(smem + OFF_Y + (5 + w) * 16384 + t * 16 + g * 2048);
                const float2 gb = *(const float2*)(smem + M_G + 224 + (8 * g + 2 * q) * 4);
                const float v0 = ac[4 * g + 0] + __uint_as_float(rv.x), v1 = ac[4 * g + 1] + __uint_as_float(rv.y);
                const float v2 = ac[4 * g + 2] + __uint_as_float(rv.z), v3 = ac[4 * g + 3] + __uint_as_float(rv.w);
                op[2 * g] = pack2(fmaf(gb.x, v0, bf_lo(x1p[2 * g])), fmaf(gb.y, v1, bf_hi(x1p[2 * g])));
                op[2 * g + 1] = pack2(fmaf(gb.x, v2, bf_lo(x1p[2 * g + 1])), fmaf(gb.y, v3, bf_hi(x1p[2 * g + 1])));
            }
            WAIT(B_EMPTY + 1, 0);
            const uint32_t oc = sb + OUT_STAGE + warp * 1792;
            const uint32_t oa = oc + (((lane >> 3) & 1) * 8 + (lane & 7)) * 112 + (lane >> 4) * 16;
            stsm4(oa, op[0], op[1], op[2], op[3]); stsm4(oa + 32, op[4], op[5], op[6], op[7]); stsm4(oa + 64, op[8], op[9], op[10], op[11]);
            asm volatile("stmatrix.sync.aligned.m8n8.x2.shared.b16 [%0], {%1,%2};" ::"r"(oa + 96), "r"(op[12]), "r"(op[13]));
            fence_async_smem();
            __syncwarp();
            asm volatile("{\n.reg .pred p;\nelect.sync _|p, 0xffffffff;\n@p cp.async.bulk.tensor.3d.global.shared::cta.bulk_group [%0, {%2, %3, %4}], [%1];\n"
                         "cp.async.bulk.commit_group;\ncp.async.bulk.wait_group.read 0;\n}" ::"l"(&p.om), "r"(oc), "r"(56 * j), "r"(128 * r + 64 * w + 16 * wi), "r"(0) : "memory");
        }
        PROFC(26);
        bar_sync(1 + w, 128);
        if (wi == 0) warp_arrive(BAR(B_DONE));
        return;
    }
    helper_late(p, r, j, warp PROF_ARGS);
}

#undef act
typedef CUresult (*EncodeFn)(CUtensorMap*, CUtensorMapDataType, cuuint32_t, void*, const cuuint64_t*, const cuuint64_t*, const cuuint32_t*,
                             const cuuint32_t*, CUtensorMapInterleave, CUtensorMapSwizzle, CUtensorMapL2promotion, CUtensorMapFloatOOBfill);

static void make_map(EncodeFn fn, CUtensorMap* m, const void* ptr, uint64_t d0, uint64_t d1, uint64_t d2, uint64_t s1, uint64_t s2,
                     uint32_t b0, uint32_t b1, uint32_t b2, CUtensorMapSwizzle sw) {
    cuuint64_t dims[3] = {d0, d1, d2}, strides[2] = {s1, s2};
    cuuint32_t box[3] = {b0, b1, b2}, es[3] = {1, 1, 1};
    CUresult rc = fn(m, CU_TENSOR_MAP_DATA_TYPE_BFLOAT16, 3, (void*)ptr, dims, strides, box, es, CU_TENSOR_MAP_INTERLEAVE_NONE, sw,
                     CU_TENSOR_MAP_L2_PROMOTION_L2_128B, CU_TENSOR_MAP_FLOAT_OOB_FILL_NONE);
    (void)rc;
}

extern "C" void kernel_launch(void* const* d_in, const int* in_sizes, int n_in, void* d_out, int out_size) {
    (void)in_sizes; (void)n_in; (void)out_size;
    static EncodeFn fn = nullptr;
    static uint32_t* act_base = nullptr;
    if (!fn) {
        cudaDriverEntryPointQueryResult st;
        cudaGetDriverEntryPoint("cuTensorMapEncodeTiled", (void**)&fn, cudaEnableDefault, &st);
        void* a = nullptr;
        cudaGetSymbolAddress(&a, g_act);
        act_base = (uint32_t*)(((uintptr_t)a + 0xFFFFF) & ~(uintptr_t)0xFFFFF);
        cudaFuncSetAttribute(fused_block_kernel, cudaFuncAttributeMaxDynamicSharedMemorySize, SMEM_BYTES);
    }
    Params p;
    p.x = (const bf16*)d_in[0];
    const bf16* wqkv = (const bf16*)d_in[1];
    p.wqkv = wqkv;
    p.wop = (const bf16*)d_in[2];
    p.wg = (const bf16*)d_in[4];
    p.wu = (const bf16*)d_in[5];
    p.wd = (const bf16*)d_in[6];
    p.c = (const bf16*)d_in[7];
    p.wmod = (const bf16*)d_in[8];
    p.out = (bf16*)d_out;
    p.zero = 0;
    p.actb = act_base;
    make_map(fn, &p.wm, p.wmod, 2688, 448, 1, 5376, 5376 * 448, 16, 224, 1, CU_TENSOR_MAP_SWIZZLE_NONE);
    make_map(fn, &p.wm2, p.wmod, 2688, 448, 1, 5376, 5376 * 448, 32, 224, 1, CU_TENSOR_MAP_SWIZZLE_NONE);
    make_map(fn, &p.om, p.out, 448, 2048, 1, 896, 896 * 2048, 56, 16, 1, CU_TENSOR_MAP_SWIZZLE_NONE);
    make_map(fn, &p.xm, p.x, 448, 2048, 1, 896, 896 * 2048, 64, 128, 1, CU_TENSOR_MAP_SWIZZLE_128B);
    make_map(fn, &p.qkv, wqkv, 1344, 448, 1, 2688, 2688 * 448, 64, 224, 1, CU_TENSOR_MAP_SWIZZLE_128B);
    make_map(fn, &p.wo, p.wop, 448, 448, 1, 896, 896 * 448, 64, 224, 1, CU_TENSOR_MAP_SWIZZLE_128B);
    make_map(fn, &p.ga, p.wg, 64, 448, 28, 3584, 128, 64, 32, 2, CU_TENSOR_MAP_SWIZZLE_128B);
    make_map(fn, &p.ua, p.wu, 64, 448, 28, 3584, 128, 64, 32, 2, CU_TENSOR_MAP_SWIZZLE_128B);
    make_map(fn, &p.gb, p.wg, 64, 448, 28, 3584, 128, 64, 64, 1, CU_TENSOR_MAP_SWIZZLE_128B);
    make_map(fn, &p.ub, p.wu, 64, 448, 28, 3584, 128, 64, 64, 1, CU_TENSOR_MAP_SWIZZLE_128B);
    make_map(fn, &p.gc, p.wg, 32, 448, 56, 3584, 64, 32, 64, 1, CU_TENSOR_MAP_SWIZZLE_64B);
    make_map(fn, &p.uc, p.wu, 32, 448, 56, 3584, 64, 32, 64, 1, CU_TENSOR_MAP_SWIZZLE_64B);
    make_map(fn, &p.dn, p.wd, 8, 1792, 56, 896, 16, 8, 32, 7, CU_TENSOR_MAP_SWIZZLE_NONE);
    fused_block_kernel<<<NCTA, 384, SMEM_BYTES>>>(p);
}
```

```cpp
#include <cuda_runtime.h>
#include <cuda_bf16.h>
#include <cuda.h>
#include <stdint.h>

typedef __nv_bfloat16 bf16;

template<uint64_t CA, uint64_t CB> __device__ __forceinline__ void wgmma_sk_160(float* d, uint32_t da, uint32_t db, int sd) {
  asm volatile("{\n.reg .pred p;\n.reg .b64 a, b;\nsetp.ne.b32 p, %82, 0;\nmov.b64 a, {%80, %83};\nmov.b64 b, {%81, %84};\n"
    "wgmma.mma_async.sync.aligned.m64n160k16.f32.bf16.bf16 {%0,%1,%2,%3,%4,%5,%6,%7,%8,%9,%10,%11,%12,%13,%14,%15,%16,%17,%18,%19,%20,%21,%22,%23,%24,%25,%26,%27,%28,%29,%30,%31,%32,%33,%34,%35,%36,%37,%38,%39,%40,%41,%42,%43,%44,%45,%46,%47,%48,%49,%50,%51,%52,%53,%54,%55,%56,%57,%58,%59,%60,%61,%62,%63,%64,%65,%66,%67,%68,%69,%70,%71,%72,%73,%74,%75,%76,%77,%78,%79}, a, b, p, 1, 1, 0, 0;\n}\n"
    : "+f"(d[0]),"+f"(d[1]),"+f"(d[2]),"+f"(d[3]),"+f"(d[4]),"+f"(d[5]),"+f"(d[6]),"+f"(d[7]),"+f"(d[8]),"+f"(d[9]),"+f"(d[10]),"+f"(d[11]),"+f"(d[12]),"+f"(d[13]),"+f"(d[14]),"+f"(d[15]),"+f"(d[16]),"+f"(d[17]),"+f"(d[18]),"+f"(d[19]),"+f"(d[20]),"+f"(d[21]),"+f"(d[22]),"+f"(d[23]),"+f"(d[24]),"+f"(d[25]),"+f"(d[26]),"+f"(d[27]),"+f"(d[28]),"+f"(d[29]),"+f"(d[30]),"+f"(d[31]),"+f"(d[32]),"+f"(d[33]),"+f"(d[34]),"+f"(d[35]),"+f"(d[36]),"+f"(d[37]),"+f"(d[38]),"+f"(d[39]),"+f"(d[40]),"+f"(d[41]),"+f"(d[42]),"+f"(d[43]),"+f"(d[44]),"+f"(d[45]),"+f"(d[46]),"+f"(d[47]),"+f"(d[48]),"+f"(d[49]),"+f"(d[50]),"+f"(d[51]),"+f"(d[52]),"+f"(d[53]),"+f"(d[54]),"+f"(d[55]),"+f"(d[56]),"+f"(d[57]),"+f"(d[58]),"+f"(d[59]),"+f"(d[60]),"+f"(d[61]),"+f"(d[62]),"+f"(d[63]),"+f"(d[64]),"+f"(d[65]),"+f"(d[66]),"+f"(d[67]),"+f"(d[68]),"+f"(d[69]),"+f"(d[70]),"+f"(d[71]),"+f"(d[72]),"+f"(d[73]),"+f"(d[74]),"+f"(d[75]),"+f"(d[76]),"+f"(d[77]),"+f"(d[78]),"+f"(d[79])
    : "r"(da), "r"(db), "r"(sd), "n"((uint32_t)(CA >> 32)), "n"((uint32_t)(CB >> 32)));
}
__device__ __forceinline__ void wgmma_rl_56(float* d, uint32_t a0, uint32_t a1, uint32_t a2, uint32_t a3, uint64_t db, int sd) {
  asm volatile("{\n.reg .pred p;\nsetp.ne.b32 p, %33, 0;\n"
    "wgmma.mma_async.sync.aligned.m64n56k16.f32.bf16.bf16 {%0,%1,%2,%3,%4,%5,%6,%7,%8,%9,%10,%11,%12,%13,%14,%15,%16,%17,%18,%19,%20,%21,%22,%23,%24,%25,%26,%27}, {%28,%29,%30,%31}, %32, p, 1, 1, 1;\n}\n"
    : "+f"(d[0]),"+f"(d[1]),"+f"(d[2]),"+f"(d[3]),"+f"(d[4]),"+f"(d[5]),"+f"(d[6]),"+f"(d[7]),"+f"(d[8]),"+f"(d[9]),"+f"(d[10]),"+f"(d[11]),"+f"(d[12]),"+f"(d[13]),"+f"(d[14]),"+f"(d[15]),"+f"(d[16]),"+f"(d[17]),"+f"(d[18]),"+f"(d[19]),"+f"(d[20]),"+f"(d[21]),"+f"(d[22]),"+f"(d[23]),"+f"(d[24]),"+f"(d[25]),"+f"(d[26]),"+f"(d[27])
    : "r"(a0), "r"(a1), "r"(a2), "r"(a3), "l"(db), "r"(sd));
}
template<uint64_t CA, uint64_t CB> __device__ __forceinline__ void wgmma_ss_56(float* d, uint32_t da, uint32_t db, int sd) {
  asm volatile("{\n.reg .pred p;\n.reg .b64 a, b;\nsetp.ne.b32 p, %30, 0;\nmov.b64 a, {%28, %31};\nmov.b64 b, {%29, %32};\n"
    "wgmma.mma_async.sync.aligned.m64n56k16.f32.bf16.bf16 {%0,%1,%2,%3,%4,%5,%6,%7,%8,%9,%10,%11,%12,%13,%14,%15,%16,%17,%18,%19,%20,%21,%22,%23,%24,%25,%26,%27}, a, b, p, 1, 1, 0, 1;\n}\n"
    : "+f"(d[0]),"+f"(d[1]),"+f"(d[2]),"+f"(d[3]),"+f"(d[4]),"+f"(d[5]),"+f"(d[6]),"+f"(d[7]),"+f"(d[8]),"+f"(d[9]),"+f"(d[10]),"+f"(d[11]),"+f"(d[12]),"+f"(d[13]),"+f"(d[14]),"+f"(d[15]),"+f"(d[16]),"+f"(d[17]),"+f"(d[18]),"+f"(d[19]),"+f"(d[20]),"+f"(d[21]),"+f"(d[22]),"+f"(d[23]),"+f"(d[24]),"+f"(d[25]),"+f"(d[26]),"+f"(d[27])
    : "r"(da), "r"(db), "r"(sd), "n"((uint32_t)(CA >> 32)), "n"((uint32_t)(CB >> 32)));
}
__device__ __forceinline__ void wgmma_rl_256(float* d, uint32_t a0, uint32_t a1, uint32_t a2, uint32_t a3, uint64_t db, int sd) {
  asm volatile("{\n.reg .pred p;\nsetp.ne.b32 p, %133, 0;\n"
    "wgmma.mma_async.sync.aligned.m64n256k16.f32.bf16.bf16 {%0,%1,%2,%3,%4,%5,%6,%7,%8,%9,%10,%11,%12,%13,%14,%15,%16,%17,%18,%19,%20,%21,%22,%23,%24,%25,%26,%27,%28,%29,%30,%31,%32,%33,%34,%35,%36,%37,%38,%39,%40,%41,%42,%43,%44,%45,%46,%47,%48,%49,%50,%51,%52,%53,%54,%55,%56,%57,%58,%59,%60,%61,%62,%63,%64,%65,%66,%67,%68,%69,%70,%71,%72,%73,%74,%75,%76,%77,%78,%79,%80,%81,%82,%83,%84,%85,%86,%87,%88,%89,%90,%91,%92,%93,%94,%95,%96,%97,%98,%99,%100,%101,%102,%103,%104,%105,%106,%107,%108,%109,%110,%111,%112,%113,%114,%115,%116,%117,%118,%119,%120,%121,%122,%123,%124,%125,%126,%127}, {%128,%129,%130,%131}, %132, p, 1, 1, 1;\n}\n"
    : "+f"(d[0]),"+f"(d[1]),"+f"(d[2]),"+f"(d[3]),"+f"(d[4]),"+f"(d[5]),"+f"(d[6]),"+f"(d[7]),"+f"(d[8]),"+f"(d[9]),"+f"(d[10]),"+f"(d[11]),"+f"(d[12]),"+f"(d[13]),"+f"(d[14]),"+f"(d[15]),"+f"(d[16]),"+f"(d[17]),"+f"(d[18]),"+f"(d[19]),"+f"(d[20]),"+f"(d[21]),"+f"(d[22]),"+f"(d[23]),"+f"(d[24]),"+f"(d[25]),"+f"(d[26]),"+f"(d[27]),"+f"(d[28]),"+f"(d[29]),"+f"(d[30]),"+f"(d[31]),"+f"(d[32]),"+f"(d[33]),"+f"(d[34]),"+f"(d[35]),"+f"(d[36]),"+f"(d[37]),"+f"(d[38]),"+f"(d[39]),"+f"(d[40]),"+f"(d[41]),"+f"(d[42]),"+f"(d[43]),"+f"(d[44]),"+f"(d[45]),"+f"(d[46]),"+f"(d[47]),"+f"(d[48]),"+f"(d[49]),"+f"(d[50]),"+f"(d[51]),"+f"(d[52]),"+f"(d[53]),"+f"(d[54]),"+f"(d[55]),"+f"(d[56]),"+f"(d[57]),"+f"(d[58]),"+f"(d[59]),"+f"(d[60]),"+f"(d[61]),"+f"(d[62]),"+f"(d[63]),"+f"(d[64]),"+f"(d[65]),"+f"(d[66]),"+f"(d[67]),"+f"(d[68]),"+f"(d[69]),"+f"(d[70]),"+f"(d[71]),"+f"(d[72]),"+f"(d[73]),"+f"(d[74]),"+f"(d[75]),"+f"(d[76]),"+f"(d[77]),"+f"(d[78]),"+f"(d[79]),"+f"(d[80]),"+f"(d[81]),"+f"(d[82]),"+f"(d[83]),"+f"(d[84]),"+f"(d[85]),"+f"(d[86]),"+f"(d[87]),"+f"(d[88]),"+f"(d[89]),"+f"(d[90]),"+f"(d[91]),"+f"(d[92]),"+f"(d[93]),"+f"(d[94]),"+f"(d[95]),"+f"(d[96]),"+f"(d[97]),"+f"(d[98]),"+f"(d[99]),"+f"(d[100]),"+f"(d[101]),"+f"(d[102]),"+f"(d[103]),"+f"(d[104]),"+f"(d[105]),"+f"(d[106]),"+f"(d[107]),"+f"(d[108]),"+f"(d[109]),"+f"(d[110]),"+f"(d[111]),"+f"(d[112]),"+f"(d[113]),"+f"(d[114]),"+f"(d[115]),"+f"(d[116]),"+f"(d[117]),"+f"(d[118]),"+f"(d[119]),"+f"(d[120]),"+f"(d[121]),"+f"(d[122]),"+f"(d[123]),"+f"(d[124]),"+f"(d[125]),"+f"(d[126]),"+f"(d[127])
    : "r"(a0), "r"(a1), "r"(a2), "r"(a3), "l"(db), "r"(sd));
}
template<uint64_t CA, uint64_t CB> __device__ __forceinline__ void wgmma_ss_128(float* d, uint32_t da, uint32_t db, int sd) {
  asm volatile("{\n.reg .pred p;\n.reg .b64 a, b;\nsetp.ne.b32 p, %66, 0;\nmov.b64 a, {%64, %67};\nmov.b64 b, {%65, %68};\n"
    "wgmma.mma_async.sync.aligned.m64n128k16.f32.bf16.bf16 {%0,%1,%2,%3,%4,%5,%6,%7,%8,%9,%10,%11,%12,%13,%14,%15,%16,%17,%18,%19,%20,%21,%22,%23,%24,%25,%26,%27,%28,%29,%30,%31,%32,%33,%34,%35,%36,%37,%38,%39,%40,%41,%42,%43,%44,%45,%46,%47,%48,%49,%50,%51,%52,%53,%54,%55,%56,%57,%58,%59,%60,%61,%62,%63}, a, b, p, 1, 1, 0, 1;\n}\n"
    : "+f"(d[0]),"+f"(d[1]),"+f"(d[2]),"+f"(d[3]),"+f"(d[4]),"+f"(d[5]),"+f"(d[6]),"+f"(d[7]),"+f"(d[8]),"+f"(d[9]),"+f"(d[10]),"+f"(d[11]),"+f"(d[12]),"+f"(d[13]),"+f"(d[14]),"+f"(d[15]),"+f"(d[16]),"+f"(d[17]),"+f"(d[18]),"+f"(d[19]),"+f"(d[20]),"+f"(d[21]),"+f"(d[22]),"+f"(d[23]),"+f"(d[24]),"+f"(d[25]),"+f"(d[26]),"+f"(d[27]),"+f"(d[28]),"+f"(d[29]),"+f"(d[30]),"+f"(d[31]),"+f"(d[32]),"+f"(d[33]),"+f"(d[34]),"+f"(d[35]),"+f"(d[36]),"+f"(d[37]),"+f"(d[38]),"+f"(d[39]),"+f"(d[40]),"+f"(d[41]),"+f"(d[42]),"+f"(d[43]),"+f"(d[44]),"+f"(d[45]),"+f"(d[46]),"+f"(d[47]),"+f"(d[48]),"+f"(d[49]),"+f"(d[50]),"+f"(d[51]),"+f"(d[52]),"+f"(d[53]),"+f"(d[54]),"+f"(d[55]),"+f"(d[56]),"+f"(d[57]),"+f"(d[58]),"+f"(d[59]),"+f"(d[60]),"+f"(d[61]),"+f"(d[62]),"+f"(d[63])
    : "r"(da), "r"(db), "r"(sd), "n"((uint32_t)(CA >> 32)), "n"((uint32_t)(CB >> 32)));
}
template<uint64_t CA, uint64_t CB> __device__ __forceinline__ void wgmma_ss_64(float* d, uint32_t da, uint32_t db, int sd) {
  asm volatile("{\n.reg .pred p;\n.reg .b64 a, b;\nsetp.ne.b32 p, %34, 0;\nmov.b64 a, {%32, %35};\nmov.b64 b, {%33, %36};\n"
    "wgmma.mma_async.sync.aligned.m64n64k16.f32.bf16.bf16 {%0,%1,%2,%3,%4,%5,%6,%7,%8,%9,%10,%11,%12,%13,%14,%15,%16,%17,%18,%19,%20,%21,%22,%23,%24,%25,%26,%27,%28,%29,%30,%31}, a, b, p, 1, 1, 0, 1;\n}\n"
    : "+f"(d[0]),"+f"(d[1]),"+f"(d[2]),"+f"(d[3]),"+f"(d[4]),"+f"(d[5]),"+f"(d[6]),"+f"(d[7]),"+f"(d[8]),"+f"(d[9]),"+f"(d[10]),"+f"(d[11]),"+f"(d[12]),"+f"(d[13]),"+f"(d[14]),"+f"(d[15]),"+f"(d[16]),"+f"(d[17]),"+f"(d[18]),"+f"(d[19]),"+f"(d[20]),"+f"(d[21]),"+f"(d[22]),"+f"(d[23]),"+f"(d[24]),"+f"(d[25]),"+f"(d[26]),"+f"(d[27]),"+f"(d[28]),"+f"(d[29]),"+f"(d[30]),"+f"(d[31])
    : "r"(da), "r"(db), "r"(sd), "n"((uint32_t)(CA >> 32)), "n"((uint32_t)(CB >> 32)));
}
template<uint64_t CA, uint64_t CB> __device__ __forceinline__ void wgmma_ss_112(float* d, uint32_t da, uint32_t db, int sd) {
  asm volatile("{\n.reg .pred p;\n.reg .b64 a, b;\nsetp.ne.b32 p, %58, 0;\nmov.b64 a, {%56, %59};\nmov.b64 b, {%57, %60};\n"
    "wgmma.mma_async.sync.aligned.m64n112k16.f32.bf16.bf16 {%0,%1,%2,%3,%4,%5,%6,%7,%8,%9,%10,%11,%12,%13,%14,%15,%16,%17,%18,%19,%20,%21,%22,%23,%24,%25,%26,%27,%28,%29,%30,%31,%32,%33,%34,%35,%36,%37,%38,%39,%40,%41,%42,%43,%44,%45,%46,%47,%48,%49,%50,%51,%52,%53,%54,%55}, a, b, p, 1, 1, 0, 1;\n}\n"
    : "+f"(d[0]),"+f"(d[1]),"+f"(d[2]),"+f"(d[3]),"+f"(d[4]),"+f"(d[5]),"+f"(d[6]),"+f"(d[7]),"+f"(d[8]),"+f"(d[9]),"+f"(d[10]),"+f"(d[11]),"+f"(d[12]),"+f"(d[13]),"+f"(d[14]),"+f"(d[15]),"+f"(d[16]),"+f"(d[17]),"+f"(d[18]),"+f"(d[19]),"+f"(d[20]),"+f"(d[21]),"+f"(d[22]),"+f"(d[23]),"+f"(d[24]),"+f"(d[25]),"+f"(d[26]),"+f"(d[27]),"+f"(d[28]),"+f"(d[29]),"+f"(d[30]),"+f"(d[31]),"+f"(d[32]),"+f"(d[33]),"+f"(d[34]),"+f"(d[35]),"+f"(d[36]),"+f"(d[37]),"+f"(d[38]),"+f"(d[39]),"+f"(d[40]),"+f"(d[41]),"+f"(d[42]),"+f"(d[43]),"+f"(d[44]),"+f"(d[45]),"+f"(d[46]),"+f"(d[47]),"+f"(d[48]),"+f"(d[49]),"+f"(d[50]),"+f"(d[51]),"+f"(d[52]),"+f"(d[53]),"+f"(d[54]),"+f"(d[55])
    : "r"(da), "r"(db), "r"(sd), "n"((uint32_t)(CA >> 32)), "n"((uint32_t)(CB >> 32)));
}
__device__ __forceinline__ void wgmma_rl_112(float* d, uint32_t a0, uint32_t a1, uint32_t a2, uint32_t a3, uint64_t db, int sd) {
  asm volatile("{\n.reg .pred p;\nsetp.ne.b32 p, %61, 0;\n"
    "wgmma.mma_async.sync.aligned.m64n112k16.f32.bf16.bf16 {%0,%1,%2,%3,%4,%5,%6,%7,%8,%9,%10,%11,%12,%13,%14,%15,%16,%17,%18,%19,%20,%21,%22,%23,%24,%25,%26,%27,%28,%29,%30,%31,%32,%33,%34,%35,%36,%37,%38,%39,%40,%41,%42,%43,%44,%45,%46,%47,%48,%49,%50,%51,%52,%53,%54,%55}, {%56,%57,%58,%59}, %60, p, 1, 1, 1;\n}\n"
    : "+f"(d[0]),"+f"(d[1]),"+f"(d[2]),"+f"(d[3]),"+f"(d[4]),"+f"(d[5]),"+f"(d[6]),"+f"(d[7]),"+f"(d[8]),"+f"(d[9]),"+f"(d[10]),"+f"(d[11]),"+f"(d[12]),"+f"(d[13]),"+f"(d[14]),"+f"(d[15]),"+f"(d[16]),"+f"(d[17]),"+f"(d[18]),"+f"(d[19]),"+f"(d[20]),"+f"(d[21]),"+f"(d[22]),"+f"(d[23]),"+f"(d[24]),"+f"(d[25]),"+f"(d[26]),"+f"(d[27]),"+f"(d[28]),"+f"(d[29]),"+f"(d[30]),"+f"(d[31]),"+f"(d[32]),"+f"(d[33]),"+f"(d[34]),"+f"(d[35]),"+f"(d[36]),"+f"(d[37]),"+f"(d[38]),"+f"(d[39]),"+f"(d[40]),"+f"(d[41]),"+f"(d[42]),"+f"(d[43]),"+f"(d[44]),"+f"(d[45]),"+f"(d[46]),"+f"(d[47]),"+f"(d[48]),"+f"(d[49]),"+f"(d[50]),"+f"(d[51]),"+f"(d[52]),"+f"(d[53]),"+f"(d[54]),"+f"(d[55])
    : "r"(a0), "r"(a1), "r"(a2), "r"(a3), "l"(db), "r"(sd));
}

constexpr int DM = 448;
constexpr int NCTA = 128;
#define WIN 6
#define NPRE 14
#define VPRE 3
constexpr int SPIN_LIMIT = 1 << 22;

constexpr uint32_t OFF_X = 0, OFF_Y = 114688, OFF_MISC = 229376, SMEM_BYTES = 232448;
constexpr uint32_t Y_VR = 0, Y_K = 28672, Y_KOWN = 57344, Y_VOWN = 71680, Y_Q = 86016;
constexpr uint32_t HALF = 57344;
constexpr uint32_t X_STAT = 49152;
constexpr uint32_t OUT_STAGE = 16384;
constexpr uint32_t M_BAR = OFF_MISC;
constexpr uint32_t M_ST = OFF_MISC + 512;
constexpr uint32_t M_G = OFF_MISC + 2304;
constexpr uint32_t M_EPOCH = OFF_MISC + 3040;
enum { B_XFULL = 0, B_FULLK = 7, B_FULLV = 8, B_FULLQ, B_KRFULL, B_VRFULL, B_WOFULL, B_XCH, B_MOD1 = 15, B_FULL = 16, B_WMFULL = 30,
       B_EMPTY = 32, B_XFREE = B_EMPTY + 12, B_GEMV, B_PEER,
       B_PUB = 47,
       B_WMFREE = 56, B_HRDY, B_GFULL = B_HRDY + 3, B_DONE = 31, B_DUMMY = B_GEMV };

__device__ uint32_t g_ticket;
__device__ __align__(128) uint32_t g_mod[8 * 6 * DM];
__device__ __align__(128) uint32_t g_flag[144 * 128];
constexpr int RB_WORDS = 262144, RB_KV = 0, RB_O = 57344, RB_X1 = 86016, RB_H2 = 143360, RB_ST = 258048;
__device__ __align__(128) uint32_t g_act[17 * RB_WORDS];
__device__ __align__(128) uint32_t g_wd[56 * 4 * 1792];
#define PROFH(id)
#define PROFH1(id)
#define PROFC(id)

struct alignas(64) Params {
    CUtensorMap wm, wm2, om, xm, qkv, wo, ga, ua, gb, ub, gc, uc, dn;
    const bf16 *x, *c, *wqkv, *wmod, *wg, *wu, *wd, *wop;
    bf16* out;
    uint32_t* actb;
    uint32_t zero;
};

__device__ __forceinline__ void mbar_init(uint32_t bar, int cnt) { asm volatile("mbarrier.init.shared::cta.b64 [%0], %1;" ::"r"(bar), "r"(cnt) : "memory"); }
__device__ __forceinline__ void mbar_arrive(uint32_t bar) { asm volatile("mbarrier.arrive.shared::cta.b64 _, [%0];" ::"r"(bar) : "memory"); }
__device__ __forceinline__ void mbar_wait(uint32_t bar, uint32_t parity) {
    uint32_t ok; int n = 0;
    do {
        asm volatile("{\n.reg .pred p;\nmbarrier.try_wait.parity.shared::cta.b64 p, [%1], %2;\nselp.u32 %0, 1, 0, p;\n}" : "=r"(ok) : "r"(bar), "r"(parity) : "memory");
        if (++n > SPIN_LIMIT) __trap();
    } while (!ok);
}
__device__ __forceinline__ void mbar_wait_c(uint32_t bar, uint32_t parity) {
    asm volatile("{\n.reg .pred p;\nWL:\nmbarrier.try_wait.parity.shared::cta.b64 p, [%0], %1, 0x989680;\n@!p bra WL;\n}" ::"r"(bar), "r"(parity) : "memory");
}
__device__ __forceinline__ void mbar_wait_cluster(uint32_t bar, uint32_t parity) {
    asm volatile("{\n.reg .pred p;\nWL:\nmbarrier.try_wait.parity.acquire.cluster.shared::cta.b64 p, [%0], %1, 0x989680;\n@!p bra WL;\n}" ::"r"(bar), "r"(parity) : "memory");
}
__device__ __forceinline__ void warp_arrive(uint32_t bar) {
    __syncwarp();
    asm volatile("{\n.reg .pred p;\nelect.sync _|p, 0xffffffff;\n@p mbarrier.arrive.shared::cta.b64 _, [%0];\n}" ::"r"(bar) : "memory");
}
__device__ __forceinline__ int opaque(int v) { return __shfl_sync(~0u, v, 0); }
__device__ __forceinline__ int fresh_tid() { int v; asm volatile("mov.u32 %0, %%tid.x;" : "=r"(v)); return v; }
__device__ __forceinline__ void bar_sync(int id, int n) { asm volatile("bar.sync %0, %1;" ::"r"(id), "r"(n) : "memory"); }
__device__ __forceinline__ void bar_arrive(int id, int n) { asm volatile("bar.arrive %0, %1;" ::"r"(id), "r"(n) : "memory"); }
__device__ __forceinline__ void fence_async_smem() { asm volatile("fence.proxy.async.shared::cta;" ::: "memory"); }
__device__ __forceinline__ void fence_async_global() { asm volatile("fence.proxy.async.global;" ::: "memory"); }
__device__ __forceinline__ void fence_gpu() { asm volatile("fence.release.gpu;" ::: "memory"); }
__device__ __forceinline__ void expect_e(uint32_t bar, uint32_t bytes) {
    asm volatile("{\n.reg .pred p;\nelect.sync _|p, 0xffffffff;\n@p mbarrier.arrive.expect_tx.shared::cta.b64 _, [%0], %1;\n}" ::"r"(bar), "r"(bytes) : "memory");
}
__device__ __forceinline__ void tma3_e(uint32_t dst, const CUtensorMap* m, int c0, int c1, int c2, uint32_t bar) {
    asm volatile("{\n.reg .pred p;\nelect.sync _|p, 0xffffffff;\n@p cp.async.bulk.tensor.3d.shared::cluster.global.mbarrier::complete_tx::bytes [%0], [%1, {%3, %4, %5}], [%2];\n}"
                 ::"r"(dst), "l"(m), "r"(bar), "r"(c0), "r"(c1), "r"(c2) : "memory");
}
__device__ __forceinline__ void bulk_e(uint32_t dst, const void* src, uint32_t bytes, uint32_t bar) {
    asm volatile("{\n.reg .pred p;\nelect.sync _|p, 0xffffffff;\n@p cp.async.bulk.shared::cluster.global.mbarrier::complete_tx::bytes [%0], [%1], %2, [%3];\n}"
                 ::"r"(dst), "l"(src), "r"(bytes), "r"(bar) : "memory");
}
__device__ __forceinline__ void init_e(uint32_t bar, int cnt) {
    asm volatile("{\n.reg .pred p;\nelect.sync _|p, 0xffffffff;\n@p mbarrier.init.shared::cta.b64 [%0], %1;\n}" ::"r"(bar), "r"(cnt) : "memory");
}
__device__ __forceinline__ void l2_prefetch_e(const void* src, uint32_t bytes) {
    asm volatile("{\n.reg .pred p;\nelect.sync _|p, 0xffffffff;\n@p cp.async.bulk.prefetch.L2.global [%0], %1;\n}" ::"l"(src), "r"(bytes) : "memory");
}
__device__ __forceinline__ uint32_t ld_relaxed(const uint32_t* p) { uint32_t v; asm volatile("ld.relaxed.gpu.global.u32 %0, [%1];" : "=r"(v) : "l"(p) : "memory"); return v; }
__device__ __forceinline__ void st_relaxed(uint32_t* p, uint32_t v) { asm volatile("st.relaxed.gpu.global.u32 [%0], %1;" ::"l"(p), "r"(v) : "memory"); }
__device__ __forceinline__ uint4 ld_relaxed4(const uint4* p) { uint4 v; asm volatile("ld.relaxed.gpu.global.v4.u32 {%0,%1,%2,%3}, [%4];" : "=r"(v.x), "=r"(v.y), "=r"(v.z), "=r"(v.w) : "l"(p) : "memory"); return v; }
__device__ __forceinline__ uint4 lds4(uint32_t a) { uint4 v; asm volatile("ld.shared.v4.u32 {%0,%1,%2,%3}, [%4];" : "=r"(v.x), "=r"(v.y), "=r"(v.z), "=r"(v.w) : "r"(a) : "memory"); return v; }
__device__ __forceinline__ float2 lds2f(uint32_t a) { float2 v; asm volatile("ld.shared.v2.f32 {%0,%1}, [%2];" : "=f"(v.x), "=f"(v.y) : "r"(a) : "memory"); return v; }
__device__ __forceinline__ uint32_t lds1(uint32_t a) { uint32_t v; asm volatile("ld.shared.u32 %0, [%1];" : "=r"(v) : "r"(a) : "memory"); return v; }
__device__ __forceinline__ void sts4(uint32_t a, uint4 v) { asm volatile("st.shared.v4.u32 [%0], {%1,%2,%3,%4};" ::"r"(a), "r"(v.x), "r"(v.y), "r"(v.z), "r"(v.w) : "memory"); }
__device__ __forceinline__ void sts1(uint32_t a, uint32_t v) { asm volatile("st.shared.u32 [%0], %1;" ::"r"(a), "r"(v) : "memory"); }
__device__ __forceinline__ void stsm4(uint32_t a, uint32_t r0, uint32_t r1, uint32_t r2, uint32_t r3) {
    asm volatile("stmatrix.sync.aligned.m8n8.x4.shared.b16 [%0], {%1,%2,%3,%4};" ::"r"(a), "r"(r0), "r"(r1), "r"(r2), "r"(r3));
}
__device__ __forceinline__ uint32_t pack2(float lo, float hi) { uint32_t r; asm("cvt.rn.bf16x2.f32 %0, %1, %2;" : "=r"(r) : "f"(hi), "f"(lo)); return r; }
__device__ __forceinline__ uint32_t pack2_relu(float lo, float hi) { uint32_t r; asm("cvt.rn.relu.bf16x2.f32 %0, %1, %2;" : "=r"(r) : "f"(hi), "f"(lo)); return r; }
__device__ __forceinline__ uint32_t hfma2(uint32_t a, uint32_t b, uint32_t c) { uint32_t r; asm("fma.rn.bf16x2 %0, %1, %2, %3;" : "=r"(r) : "r"(a), "r"(b), "r"(c)); return r; }
__device__ __forceinline__ uint32_t hmul2(uint32_t a, uint32_t b) { uint32_t r; asm("mul.rn.bf16x2 %0, %1, %2;" : "=r"(r) : "r"(a), "r"(b)); return r; }
__device__ __forceinline__ float bf_lo(uint32_t v) { return __uint_as_float(v << 16); }
__device__ __forceinline__ float bf_hi(uint32_t v) { return __uint_as_float(v & 0xFFFF0000u); }
__device__ __forceinline__ float bf_round(float v) { return bf_lo(pack2(v, 0.f)); }
__device__ __forceinline__ float ex2(float x) { float r; asm("ex2.approx.ftz.f32 %0, %1;" : "=f"(r) : "f"(x)); return r; }
__device__ __forceinline__ void mma16816(float* d, uint32_t a0, uint32_t a1, uint32_t a2, uint32_t a3, uint32_t b0, uint32_t b1) {
    asm("mma.sync.aligned.m16n8k16.row.col.f32.bf16.bf16.f32 {%0,%1,%2,%3}, {%4,%5,%6,%7}, {%8,%9}, {%0,%1,%2,%3};"
        : "+f"(d[0]), "+f"(d[1]), "+f"(d[2]), "+f"(d[3]) : "r"(a0), "r"(a1), "r"(a2), "r"(a3), "r"(b0), "r"(b1));
}
__device__ __forceinline__ void mma1688(float* d, uint32_t a0, uint32_t a1, uint32_t b0) {
    asm("mma.sync.aligned.m16n8k8.row.col.f32.bf16.bf16.f32 {%0,%1,%2,%3}, {%4,%5}, {%6}, {%0,%1,%2,%3};"
        : "+f"(d[0]), "+f"(d[1]), "+f"(d[2]), "+f"(d[3]) : "r"(a0), "r"(a1), "r"(b0));
}
__device__ __forceinline__ void ldsm4(uint32_t a, uint32_t* r) {
    asm volatile("ldmatrix.sync.aligned.m8n8.x4.shared.b16 {%0,%1,%2,%3}, [%4];" : "=r"(r[0]), "=r"(r[1]), "=r"(r[2]), "=r"(r[3]) : "r"(a));
}
__device__ __forceinline__ void ldsm4t(uint32_t a, uint32_t* r) {
    asm volatile("ldmatrix.sync.aligned.m8n8.x4.trans.shared.b16 {%0,%1,%2,%3}, [%4];" : "=r"(r[0]), "=r"(r[1]), "=r"(r[2]), "=r"(r[3]) : "r"(a));
}
__device__ __forceinline__ uint32_t nz(uint32_t v) { uint32_t r; asm("max.u32 %0, %1, 1;" : "=r"(r) : "r"(v)); return r; }
__device__ __forceinline__ float rcp(float x) { float r; asm("rcp.approx.ftz.f32 %0, %1;" : "=f"(r) : "f"(x)); return r; }
__device__ __forceinline__ uint2 ld_relaxed2(const void* p) { uint2 v; asm volatile("ld.relaxed.gpu.global.v2.u32 {%0,%1}, [%2];" : "=r"(v.x), "=r"(v.y) : "l"(p) : "memory"); return v; }
__host__ __device__ constexpr uint64_t dconst(uint32_t lbo, uint32_t sbo, uint32_t swz) {
    return ((uint64_t)(lbo >> 4) << 16) | ((uint64_t)(sbo >> 4) << 32) | ((uint64_t)swz << 62);
}
__device__ __forceinline__ uint32_t mkdesc(uint32_t addr, uint64_t c) { return (uint32_t)c | ((addr & 0x3FFFF) >> 4); }
#define WG_FENCE() asm volatile("wgmma.fence.sync.aligned;" ::: "memory")
#define WG_COMMIT() asm volatile("wgmma.commit_group.sync.aligned;" ::: "memory")
#define WG_WAIT(n) asm volatile("wgmma.wait_group.sync.aligned %0;" ::"n"(n) : "memory")
template <int N> __device__ __forceinline__ void reg_fence(float* d) {
#pragma unroll
    for (int i = 0; i < N; i++) asm volatile("" : "+f"(d[i])::"memory");
}
template <int N> __device__ __forceinline__ void reg_def(float* d) {
#pragma unroll
    for (int i = 0; i < N; i++) asm volatile("" : "=f"(d[i]));
}
template <int N> __device__ __forceinline__ void reg_def(uint32_t* d) {
#pragma unroll
    for (int i = 0; i < N; i++) asm volatile("" : "=r"(d[i]));
}
__device__ __forceinline__ void wait_flags(const uint32_t* p, uint32_t target, uint32_t mask) {
    int n = 0;
    while (~__ballot_sync(~0u, ld_relaxed(p) == target) & mask) { if (++n > SPIN_LIMIT) __trap(); }
    asm volatile("fence.acquire.gpu;" ::: "memory");
}
__device__ __forceinline__ float silu_bf(uint32_t cbits) {
    const float c = __uint_as_float(cbits << 16);
    return bf_round(__fdividef(c, 1.f + fminf(ex2(-1.4426950408889634f * c), 1e30f)));
}
__device__ __forceinline__ void gemv_part(uint32_t wmbuf, int wp, int lane) {
    const uint32_t wa = wmbuf + wp * 512 + (8 * (lane >> 4) + (lane & 7)) * 32 + ((lane >> 3) & 1) * 16;
    float d[4] = {};
#pragma unroll
    for (int i = 0; i < 4; i++) {
        uint32_t A[4];
        const float2 v = lds2f(wmbuf + 28672 + (wp + 8 * i) * 32 + (lane & 3) * 8);
        ldsm4t(wa + (i < 3 || wp < 4 ? i : 0) * 4096, A);
        mma16816(d, A[0], A[1], A[2], A[3], __float_as_uint(v.x), __float_as_uint(v.y));
    }
    if ((lane & 3) == 0) {
        sts1(wmbuf + 29696 + (wp * 16 + (lane >> 2)) * 4, __float_as_uint(d[0]));
        sts1(wmbuf + 29696 + (wp * 16 + 8 + (lane >> 2)) * 4, __float_as_uint(d[2]));
    }
}
__device__ __forceinline__ uint32_t mod_word(float v, int col, uint32_t target) {
    v = bf_round(v);
    if ((col >= DM && col < 2 * DM) || (col >= 4 * DM && col < 5 * DM)) v += 1.f;
    return (pack2(v, 0.f) << 16) | (target & 0xFFFFu);
}
__device__ __forceinline__ const uint4* mod_src(int i, int r, int j, bool p2) {
    i = min(i, p2 ? 251 : 223);
    return (const uint4*)g_mod + (r & 7) * (6 * DM / 4) + (i < 224 ? (p2 ? 336 : 0) + i : (i < 238 ? 14 * j + i : 14 * j + i + 322));
}
__device__ __forceinline__ void mod_store(uint32_t sb, uint4 v, const uint4* src, int i) {
    const uint32_t tag = lds1(sb + M_EPOCH) + 1;
    while (__any_sync(~0u, (((v.x ^ tag) | (v.y ^ tag) | (v.z ^ tag) | (v.w ^ tag)) & 0xFFFFu) != 0u)) v = ld_relaxed4(src);
    if (i < 224) {
        const int isc = i >= 112, c4 = i - 112 * isc;
        const uint32_t a = sb + M_ST + (c4 >> 2) * 64 + (c4 & 1) * 32 + (c4 & 2) * 4 + (isc ? 0 : 4);
        sts1(a, __byte_perm(v.x, v.y, 0x7632));
        sts1(a + 16, __byte_perm(v.z, v.w, 0x7632));
    } else if (i < 252) {
        sts4(sb + M_G + (i - 224) * 16, make_uint4(v.x & 0xFFFF0000u, v.y & 0xFFFF0000u, v.z & 0xFFFF0000u, v.w & 0xFFFF0000u));
    }
}
__device__ __forceinline__ int pass_f(int fs, int ps) { return 224 * fs + ((fs & 1) ? (ps == 0 ? 96 : ps == 1 ? 32 : 0) : (ps == 0 ? 0 : ps == 1 ? 128 : 192)); }
__device__ __forceinline__ constexpr uint32_t slot_off(int l) { return l * 16384; }
__device__ __forceinline__ constexpr int g1_slot(int s) { return s % 7; }
__device__ __noinline__ void x1_fix(const uint32_t* g, uint32_t sa, int s) {
#pragma unroll 1
    for (int k = 4 * s; k < 4 * s + 4;) {
        const uint4 v = ld_relaxed4((const uint4*)(g + k * 256));
        sts4(sa + k * 1024, v);
        k += 2 * __all_sync(~0u, min(min(v.x, v.y), min(v.z, v.w)) != 0u);
    }
    __syncwarp();
}
struct LnRow { uint32_t nm, hi, lo; };
__device__ __forceinline__ LnRow ln_coeffs(float mean, float msq) {
    const float var = bf_round(fmaxf(msq - mean * mean, 0.f));
    float sd;
    asm("sqrt.approx.f32 %0, %1;" : "=f"(sd) : "f"(bf_round(var + 1e-5f)));
    const float inv = rcp(bf_round(sd)), hi = bf_round(inv);
    LnRow c;
    c.nm = pack2(-bf_round(mean) * hi, -bf_round(mean) * hi);
    c.hi = pack2(hi, hi);
    c.lo = pack2(inv - hi, inv - hi);
    return c;
}
__device__ __forceinline__ uint32_t ln_norm(uint32_t x, const LnRow& c) {
    return hfma2(x, c.hi, c.nm);
}
__device__ __forceinline__ uint32_t ln_mod(uint32_t y, uint32_t sc, uint32_t sh) {
    return hfma2(y, sc, sh);
}

#define LOADW bulk_e(dst, g_wd + (size_t)((f >> 5) * 4 + nq) * 1792, 7168, bar);
template <int sec> __device__ __forceinline__ void ring_loader(const Params& p, uint32_t sb_, int r_, int j_, int lane) {
    const uint32_t sb = opaque(sb_);
    const int r = opaque(r_), j = opaque(j_), nq = j >> 1, fs = 4 * (j & 1) + nq;
    const int fa = pass_f(fs, 0), fb = pass_f(fs, 1), fc = pass_f(fs, 2);
    const uint32_t* h2src = (const uint32_t*)__shfl_sync(~0u, (unsigned long long)(p.actb + (size_t)r * RB_WORDS + RB_H2), 0);
    const CUtensorMap* gmap = (const CUtensorMap*)__shfl_sync(~0u, (unsigned long long)(&p.ga + sec), 0);
#define BAR(i) (sb + M_BAR + 8 * (i))
#define kh (j & 1)
            int sl = 0;
#pragma unroll 1
            for (int s = 0; s < 28; s++) {
                if (s == 7) { wait_flags(g_flag + (8 * r + j) * 128 + 96 + lane, lds1(sb + M_EPOCH) + 1, 0xFFFFu); fence_async_global(); }
                const int ps = s < 14 ? 0 : s < 21 ? 1 : 2;
                const uint32_t half = ps < 2 ? 8192 : 4096;
                const int sp = sl;
                if (s >= 1 && s < 6) mbar_wait(BAR(B_FULL + s - 1), 0);
                mbar_wait(BAR(B_EMPTY + sp), (s >= 7 && s < 14) || s >= 21);
                expect_e(BAR(B_FULL + sp), half);
                tma3_e(sb + slot_off(sp) + sec * half, gmap + 2 * ps, 0, ps ? 64 * sl : 32 * s, ps == 0 ? fa >> 6 : ps == 1 ? fb >> 6 : fc >> 5, BAR(B_FULL + sp));
                sl = sl == 6 ? 0 : sl + 1;
            }
            if (!sec) PROFH(3);
            if (sec) asm volatile("prefetch.tensormap [%0];" ::"l"(&p.om) : "memory");
#pragma unroll 1
            for (int e = 0; e < 4; e++) {
                const uint32_t dst = sb + slot_off(e) + sec * 8192, bar = BAR(B_FULL + e);
                const int f = (e < 2 ? fa + 64 * e : e == 2 ? fb : fc) + 32 * sec;
                mbar_wait(BAR(B_EMPTY + e), 0);
                expect_e(bar, e == 3 && sec ? 0 : 7168);
                if (!(e == 3 && sec)) { LOADW }
            }
            sl = 4;
            int e = 4;
#pragma unroll 1
            for (int grp = 0; grp < 9; grp++) {
                const int ps = grp >= 6 ? 2 : grp >= 3 ? 1 : 0;
                int sidx = grp - 3 * ps;
                if (sec && sidx == 0) { mbar_wait(BAR(B_HRDY + ps), 0); fence_async_global(); }
                sidx += sidx >= nq;
                int f = pass_f(4 * kh + sidx, ps);
#pragma unroll 1
                for (int k = 4 >> ps; k > 0; k--, e++, f += 32) {
                    const uint32_t dst = sb + slot_off(sl), bar = BAR(B_FULL + sl);
                    mbar_wait(BAR(B_EMPTY + sl), e >= 12 && e < 24);
                    if (e >= WIN) mbar_wait(BAR(B_FULL + (sl >= WIN ? sl - WIN : sl + 12 - WIN)), e - WIN >= 12);
                    expect_e(bar, sec ? 8192 : 7168);
                    if (!sec) { LOADW }
                    else bulk_e(dst + 8192, h2src + f * 64, 8192, bar);
                    sl = sl == 11 ? 0 : sl + 1;
                }
            }
            if (!sec) PROFH(4);
}

#define PROF_PARAMS
#define PROF_ARGS
__device__ __noinline__ void helper_late(const Params& p, int r_, int j_, int warp_ PROF_PARAMS) {
    extern __shared__ __align__(1024) unsigned char smem[];
    const uint32_t sb = (uint32_t)__cvta_generic_to_shared(smem);
    const int r = opaque(r_), j = opaque(j_), warp = opaque(warp_), nq = j >> 1, b = 8 * r + j;
    uint32_t* const act = (uint32_t*)__shfl_sync(~0u, (unsigned long long)(p.actb + (size_t)r * RB_WORDS), 0);
    {
        const int lane = fresh_tid() & 31;
        const uint32_t target = lds1(sb + M_EPOCH) + 1;
        if (warp == 8) { expect_e(BAR(B_XCH), 7168); expect_e(BAR(B_XCH + 1), 7168); }
            if (warp == 9) {
#pragma unroll 1
                for (int kv = 0; kv < 2; kv++) {
                    mbar_wait(BAR(B_PUB + kv), 0);
                    wait_flags(g_flag + b * 128 + lane, target, (r >= 2 ? 6u : r == 1 ? 2u : 0u) << (8 * kv));
                    fence_async_global();
                    const uint32_t dst = sb + OFF_Y + (kv ? Y_VR : Y_K);
                    expect_e(BAR(B_KRFULL + kv), r >= 2 ? 28672 : r == 1 ? 14336 : 0);
                    if (r >= 2) bulk_e(dst, act - 2 * RB_WORDS + RB_KV + j * 7168 + kv * 3584, 14336, BAR(B_KRFULL + kv));
                    if (r >= 1) bulk_e(dst + 14336, act - RB_WORDS + RB_KV + j * 7168 + kv * 3584, 14336, BAR(B_KRFULL + kv));
                    if (kv == 0) { PROFH(8); }
                }
            } else if (warp == 8) {
                uint4 v[8];
                mbar_wait(BAR(B_WOFULL), 0);
#pragma unroll
                for (int k = 0; k < 8; k++) v[k] = ld_relaxed4(mod_src(lane + 32 * k, r, j, true));
#pragma unroll
                for (int k = 0; k < 8; k++) mod_store(sb, v[k], mod_src(lane + 32 * k, r, j, true), lane + 32 * k);
                warp_arrive(BAR(B_MOD1));
            } else if (warp == 11) {
                if (kh == 1 && r < 14) {
                    const uint32_t wmbuf = sb + OFF_X + HALF;
                    const int mcol = 2 * DM + 32 * (4 * r + nq);
                    mbar_wait(BAR(B_XFREE), 0);
                    tma3_e(wmbuf, &p.wm2, mcol, 0, 0, BAR(B_WMFULL));
                    tma3_e(wmbuf + 14336, &p.wm2, mcol, 224, 0, BAR(B_WMFULL));
#pragma unroll 1
                    for (int wd = lane; wd < 224; wd += 32) {
                        const uint32_t cb = __ldg((const uint32_t*)p.c + wd);
                        sts1(wmbuf + 28672 + (wd >> 3) * 32 + (wd & 3) * 8 + (wd & 4), pack2(silu_bf(cb & 0xFFFFu), silu_bf(cb >> 16)));
                    }
                    __syncwarp();
                    mbar_wait(BAR(B_WMFULL), 0);
                    const uint32_t wa = wmbuf + (8 * (lane >> 4) + (lane & 7)) * 64 + ((lane >> 3) & 1) * 16;
                    float d[2][4] = {};
#pragma unroll 4
                    for (int ks = 0; ks < 28; ks++) {
                        uint32_t A[8];
                        ldsm4t(wa + ks * 1024, A); ldsm4t(wa + ks * 1024 + 32, A + 4);
                        const float2 v = lds2f(wmbuf + 28672 + ks * 32 + (lane & 3) * 8);
                        mma16816(d[0], A[0], A[1], A[2], A[3], __float_as_uint(v.x), __float_as_uint(v.y));
                        mma16816(d[1], A[4], A[5], A[6], A[7], __float_as_uint(v.x), __float_as_uint(v.y));
                    }
                    const int q = lane & 3, col = mcol + 8 * q + (lane >> 2);
                    const uint32_t word = mod_word(q == 0 ? d[0][0] : q == 1 ? d[0][2] : q == 2 ? d[1][0] : d[1][2], col, target);
#pragma unroll
                    for (int i = 0; i < 8; i++) st_relaxed(g_mod + i * 6 * DM + col, word);
                }
                warp_arrive(BAR(B_WMFREE));
                mbar_wait(BAR(B_VRFULL), 0);
                l2_prefetch_e((const char*)p.wg + (size_t)b * 12544, 12544);
                l2_prefetch_e((const char*)p.wu + (size_t)b * 12544, 12544);
#pragma unroll 1
                for (int k = 0; k < (r < 12 ? 2 : 1); k++) {
                    const int u = 28 * kh + r + 16 * k;
                    expect_e(BAR(B_XFULL + k), 7168);
                    tma3_e(sb + OFF_Y + 102400, &p.dn, 0, 32 * u, 7 * j, BAR(B_XFULL + k));
                    tma3_e(sb + OFF_Y + 102400 + 3584, &p.dn, 0, 32 * u, 7 * (j ^ 1), BAR(B_XFULL + k));
                    mbar_wait(BAR(B_XFULL + k), 1);
                    asm volatile("{\n.reg .pred p;\nelect.sync _|p, 0xffffffff;\n@p cp.async.bulk.global.shared::cta.bulk_group [%0], [%1], 7168;\n"
                                 "cp.async.bulk.commit_group;\ncp.async.bulk.wait_group 0;\n}" ::"l"(g_wd + (size_t)(u * 4 + nq) * 1792), "r"(sb + OFF_Y + 102400) : "memory");
                    __syncwarp();
                }
                warp_arrive(BAR(B_FULLK));
                fence_gpu();
                if (lane < 16) st_relaxed(g_flag + (8 * lane + j) * 128 + 96 + r, target);
            }
        if (warp == 8 || warp == 11) {
            const int sec = warp == 11;
            if (sec) ring_loader<1>(p, sb, r, j, lane); else ring_loader<0>(p, sb, r, j, lane);
            mbar_wait(BAR(B_DONE), 0);
        } else if (warp == 9) {
#pragma unroll
            for (int ev = 0; ev < 4; ev++) { expect_e(BAR(B_GFULL + ev), ev < 2 ? HALF / 2 : 16384); expect_e(BAR(B_XFULL + 2 + ev), ev < 2 ? HALF / 2 : HALF - 16384); }
            mbar_wait(BAR(B_PUB + 2), 0);
            expect_e(BAR(B_FULLV), 4096); expect_e(BAR(B_FULLQ), 4096);
            const uint32_t* fp = g_flag + b * 128 + 32 + lane;
            const int par = (target - 1) & 1;
#pragma unroll 1
            for (int n = 0, ev = 0; ev < 4; n++) {
                if (ev == 1) mbar_wait(BAR(B_PUB + 3), 0);
                uint32_t ok = __ballot_sync(~0u, ld_relaxed(fp) == target) >> (8 * ev);
                while ((ok & 0xFFu) == 0xFFu) {
                    if (ev == 1) mbar_wait(BAR(B_FULLK), 1);
                    asm volatile("fence.acquire.gpu;" ::: "memory");
                    fence_async_global();
                    const int tile = (ev & 1) + (ev >> 1) * par * 2;
                    const uint32_t dst = sb + (ev == 0 ? OFF_X : OFF_Y + (ev & 1) * HALF), first = ev < 2 ? HALF / 2 : 16384;
                    const char* src = (const char*)(act + RB_O + ((ev >> 1) * 2 + tile) * 14336);
                    if (ev >= 2) bulk_e(sb + OFF_X + X_STAT + (ev & 1) * 49152, act + RB_ST + tile * 1024, 4096, BAR(B_FULLV + (ev & 1)));
                    bulk_e(dst, src, first, BAR(B_GFULL + ev));
                    bulk_e(dst + first, src + first, HALF - first, BAR(B_XFULL + 2 + ev));
                    if (ev) PROFH(4 + ev);
                    ev++; ok >>= 8;
                }
                if (n > SPIN_LIMIT) __trap();
            }
            mbar_wait(BAR(B_XFULL + 5), 1);
#pragma unroll 1
            for (int hf = 0; hf < 2; hf++) {
                const int tile = (par ^ 1) * 2 + hf;
                uint4* xz = (uint4*)(act + RB_X1 + tile * 14336 + j * 1792) + lane;
#pragma unroll
                for (int i = 0; i < 14; i++) xz[i * 32] = make_uint4(0, 0, 0, 0);
                ((uint4*)(act + RB_ST + (tile * 8 + j) * 128))[lane] = make_uint4(0, 0, 0, 0);
            }
#pragma unroll 1
            for (int ps = 0; ps < 3; ps++) {
                mbar_wait(BAR(B_PUB + 6 + ps), 0);
                wait_flags(g_flag + b * 128 + 64 + lane, target, (0x55u << kh) << (8 * ps));
                warp_arrive(BAR(B_HRDY + ps));
                PROFH(9 + ps);
            }
        } else {
#pragma unroll 1
            for (int k = 0; k < 9; k++) {
                uint32_t* fp = k < 2 ? g_flag + (b + 8 * lane) * 128 + k * 8 + lane : g_flag + (8 * r + lane) * 128 + 16 + k * 8 + j;
                mbar_wait(BAR(B_PUB + k), 0);
                if (k != 4 && k != 5) fence_gpu();
                if (k < 2 ? (lane == 1 || lane == 2) : lane < 8) st_relaxed(fp, target);
                if (k >= 3 && k <= 5) PROFH(k - 3);
            }
        }
    }
}

__global__ void __cluster_dims__(2, 1, 1) __launch_bounds__(384, 1) fused_block_kernel(const __grid_constant__ Params p) {
    extern __shared__ __align__(1024) unsigned char smem[];
    const uint32_t sb = (uint32_t)__cvta_generic_to_shared(smem);
    const int tid = threadIdx.x, lane = tid & 31, warp = __shfl_sync(~0u, tid >> 5, 0);
    const int m = blockIdx.x >> 1;
    int r, nq;
    if (m < 4) { r = 15; nq = m; }
    else if (m < 36) { r = (m - 4) & 7; nq = (m - 4) >> 3; }
    else { nq = (m - 36) / 7; r = m - 28 - 7 * nq; }
    const int j = opaque(2 * nq + (blockIdx.x & 1)), b = 8 * r + j, fs = 4 * kh + nq;
#define act (p.actb + (size_t)r * RB_WORDS)
    if (lane == 0 && warp < 9 && warp != 6 && warp != 7) {
        const int i0 = warp == 8 ? 0 : 8 + 8 * warp, cnt = warp == 0 || warp == 8 ? 1 : warp < 3 ? 2 : 8;
#pragma unroll
        for (int k = 0; k < 8; k++) if (i0 + k != B_WMFULL) mbar_init(BAR(i0 + k), cnt);
        if (warp == 8) mbar_init(BAR(B_WMFULL), 1);
        asm volatile("fence.mbarrier_init.release.cluster;" ::: "memory");
        fence_async_smem();
    }

    if (warp >= 8) {
        const int lane = fresh_tid() & 31;
        const bool early = kh == 0, gemv = r < 14;
        const int mcol = early ? 16 * (4 * r + nq) : 2 * DM + 32 * (4 * r + nq);
        const uint32_t wmbuf = sb + OFF_Y + HALF;
        if (warp == 8) {
            __syncwarp();
            expect_e(BAR(B_WMFULL), gemv ? 28672 >> early : 0);
            if (early && gemv) { tma3_e(wmbuf, &p.wm, mcol, 0, 0, BAR(B_WMFULL)); tma3_e(wmbuf + 7168, &p.wm, mcol, 224, 0, BAR(B_WMFULL)); }
#pragma unroll
            for (int kb = 0; kb < 7; kb++) {
                expect_e(BAR(B_XFULL + kb), 16384);
                tma3_e(sb + OFF_X + kb * 16384, &p.xm, 64 * kb, 128 * r, 0, BAR(B_XFULL + kb));
            }
        }
        asm volatile("setmaxnreg.dec.sync.aligned.u32 56;");
        if (warp == 9) {
#pragma unroll
            for (int i = 56; i < 64; i++) init_e(BAR(i), 1);
            fence_async_smem();
        }
        bar_arrive(0, 384);
        asm volatile("barrier.cluster.arrive.relaxed.aligned;" ::: "memory");
        if (warp == 8) {
            mbar_wait(BAR(B_XFULL), 0);
            l2_prefetch_e((const char*)p.wqkv + (size_t)b * 9408, 9408);
#pragma unroll 1
            for (int mt = 0; mt < 4; mt++) {
                if (mt == 1) bar_sync(9, 384);
                if (mt == 3) mbar_wait(BAR(B_WMFREE), 0);
                if (mt == 1 && early) mbar_wait(BAR(B_WMFREE), 0);
                if (mt) mbar_wait(BAR(mt == 1 ? B_FULLK : mt == 2 ? B_MOD1 : B_VRFULL), 0);
                const uint32_t bar = BAR(mt == 3 ? B_WOFULL : B_FULLK + mt), dst = sb + (mt < 2 ? OFF_Y : OFF_X) + (mt & 1) * HALF;
                const int c0 = (mt < 2 ? DM + DM * mt : 0) + 56 * j - 8 * kh;
                expect_e(bar, HALF);
                tma3_e(dst, mt == 3 ? &p.wo : &p.qkv, c0, 0, 0, bar);
                tma3_e(dst + HALF / 2, mt == 3 ? &p.wo : &p.qkv, c0, 224, 0, bar);
            }
        } else {
            if (warp == 10 && lane < 13) asm volatile("prefetch.tensormap [%0];" ::"l"(&p.wm + lane) : "memory");
            bar_sync(9, 384);
            if (warp == 11 && early) {
                const uint32_t target = lds1(sb + M_EPOCH) + 1;
                mbar_wait(BAR(B_GEMV), 0);
                float sum = 0.f;
#pragma unroll
                for (int i = 0; i < 8; i++) sum += *(const float*)(smem + OFF_Y + HALF + 29696 + (i * 16 + (lane & 15)) * 4);
                uint32_t* mg = g_mod + mcol + (lane & 15) + (lane >> 4) * 4 * 6 * DM;
                const uint32_t word = mod_word(sum, mcol, target);
                if (gemv) { st_relaxed(mg, word); st_relaxed(mg + 6 * DM, word); st_relaxed(mg + 12 * DM, word); st_relaxed(mg + 18 * DM, word); }
            }
        }
    }
    if (warp < 8) {
        const int w = (warp >> 2) ^ 1, wi = warp & 3;
#define COORDS const int t = fresh_tid() & 127, lane = t & 31, q = lane & 3, lr = lane >> 2, ra = 64 * w + 16 * wi + lr; \
        const uint32_t lx = (lane >> 4) ^ (lane & 7), mrow = (64 * w + 16 * wi + ((lane >> 3) & 1) * 8 + (lane & 7)) * 128; \
        (void)q; (void)lr; (void)ra; (void)lx; (void)mrow;
#define WAIT(i, par) mbar_wait_c(BAR(i), par)
        constexpr uint64_t DB128 = dconst(4096, 1024, 1);
        {
            const int wd = fresh_tid();
            const uint32_t cb = wd < 224 ? __ldg((const uint32_t*)p.c + wd) : 0u;
            if (wd == 255) sts1(sb + M_EPOCH, atomicAdd(&g_ticket, 1u) / NCTA);
            sts1(sb + OFF_Y + HALF + 28672 + (wd >> 3) * 32 + (wd & 3) * 8 + (wd & 4), pack2(silu_bf(cb & 0xFFFFu), silu_bf(cb >> 16)));
        }
        bar_arrive(9, 384);
        bar_sync(0, 384);
        asm volatile("barrier.cluster.arrive.relaxed.aligned;" ::: "memory");
        asm volatile("setmaxnreg.inc.sync.aligned.u32 224;");
        PROFC(0);
        uint32_t xr[16];
        {
            COORDS
            uint32_t h[112];
            LnRow ca, cb;
            const int mi = min(128 * w + t, 223);
            const uint4* msrc = mod_src(mi, r, j, false);
            uint4 mv;
            {
                float ds[4] = {}, da[2][4] = {}, db[2][4] = {};
                const uint32_t ONE2 = 0x3F803F80u;
#pragma unroll
                for (int kb = 0; kb < 7; kb++) {
                    if (kb == 0 && kh == 0) { WAIT(B_WMFULL, 0); gemv_part(sb + OFF_Y + HALF, warp, lane); warp_arrive(BAR(B_GEMV)); }
                    WAIT(B_XFULL + kb, 0);
#pragma unroll
                    for (int k4 = 0; k4 < 4; k4++) ldsm4(sb + OFF_X + mrow + kb * 16384 + (((2 * k4) ^ lx) << 4), h + 16 * kb + 4 * k4);
#pragma unroll
                    for (int k4 = 0; k4 < 4; k4++) {
                        const uint32_t* f = h + 16 * kb + 4 * k4;
                        mma16816(ds, f[0], f[1], f[2], f[3], ONE2, ONE2);
                        mma1688(da[0], f[0], f[1], f[0]); mma1688(db[0], f[0], f[1], f[1]);
                        mma1688(da[1], f[2], f[3], f[2]); mma1688(db[1], f[2], f[3], f[3]);
                    }
                }
#pragma unroll
                for (int i = 0; i < 4; i++) {
                    const int ch = 7 * j + 2 * i + (lane >> 4);
                    ldsm4(sb + OFF_X + mrow + (ch >> 3) * 16384 + (((ch ^ lane) & 7) << 4), xr + 4 * i);
                }
                mv = ld_relaxed4(msrc);
                warp_arrive(BAR(B_XFREE));
                float qa = (lr & 1) ? da[0][1] + da[1][1] : da[0][0] + da[1][0];
                float qb = (lr & 1) ? db[0][3] + db[1][3] : db[0][2] + db[1][2];
                const int src = (lane & ~3) | (lr >> 1);
                qa = __shfl_sync(~0u, qa, src);
                qb = __shfl_sync(~0u, qb, src);
                ca = ln_coeffs(ds[0] * (1.f / DM), qa * (1.f / DM));
                cb = ln_coeffs(ds[2] * (1.f / DM), qb * (1.f / DM));
#pragma unroll
                for (int i = 0; i < 4 * NPRE; i += 2) { h[i] = ln_norm(h[i], ca); h[i + 1] = ln_norm(h[i + 1], cb); }
            }
            PROFC(1);
            {
                float ak[28], av[28], aq[28];
                uint32_t kp[14], vp[14];
                const uint64_t bq0 = (DB128 & ~0xFFFFFFFFull) | (mkdesc(sb + OFF_X, DB128) + kh), bk0 = bq0 + (OFF_Y >> 4), bv0 = bk0 + (HALF >> 4);
                uint32_t* kvg = act + RB_KV + j * 7168 + (8 * w + 2 * wi) * 224 + lane;
                mod_store(sb, mv, msrc, mi);
                bar_sync(3, 256);
                if (warp == 0) warp_arrive(BAR(B_MOD1));
                WAIT(B_FULLK, 0);
                PROFC(2);
                reg_def<28>(ak);
#pragma unroll
                for (int g4 = 0; g4 < 4; g4++) {
#pragma unroll
                    for (int ks = 7 * g4; ks < 7 * g4 + 7; ks++) {
                        const uint4 st = *(const uint4*)(smem + M_ST + ks * 64 + q * 16);
                        if (ks >= NPRE) {
                            h[4 * ks] = ln_norm(h[4 * ks], ca); h[4 * ks + 1] = ln_norm(h[4 * ks + 1], cb);
                            h[4 * ks + 2] = ln_norm(h[4 * ks + 2], ca); h[4 * ks + 3] = ln_norm(h[4 * ks + 3], cb);
                        }
                        h[4 * ks] = ln_mod(h[4 * ks], st.x, st.y); h[4 * ks + 1] = ln_mod(h[4 * ks + 1], st.x, st.y);
                        h[4 * ks + 2] = ln_mod(h[4 * ks + 2], st.z, st.w); h[4 * ks + 3] = ln_mod(h[4 * ks + 3], st.z, st.w);
                    }
                    WG_FENCE();
#pragma unroll
                    for (int ks = 7 * g4; ks < 7 * g4 + 7; ks++) wgmma_rl_56(ak, h[4 * ks], h[4 * ks + 1], h[4 * ks + 2], h[4 * ks + 3], bk0 + ks * 128, ks != 0);
                }
                WG_COMMIT();
                PROFC(3);
                reg_def<28>(av);
                WG_WAIT(0);
                reg_fence<28>(ak);
#pragma unroll
                for (int g = 0; g < 7; g++) {
                    kp[2 * g] = pack2(ak[4 * g], ak[4 * g + 1]); kp[2 * g + 1] = pack2(ak[4 * g + 2], ak[4 * g + 3]);
                    kvg[g * 32] = kp[2 * g]; kvg[224 + g * 32] = kp[2 * g + 1];
                }
                warp_arrive(BAR(B_PUB));
                PROFC(4);
                WAIT(B_FULLV, 0);
                WG_FENCE();
#pragma unroll
                for (int ks = 0; ks < 28; ks++) wgmma_rl_56(av, h[4 * ks], h[4 * ks + 1], h[4 * ks + 2], h[4 * ks + 3], bv0 + ks * 128, ks != 0);
                WG_COMMIT();
                reg_def<28>(aq);
                WAIT(B_FULLQ, 0);
                WG_FENCE();
#pragma unroll
                for (int ks = 0; ks < VPRE; ks++) wgmma_rl_56(aq, h[4 * ks], h[4 * ks + 1], h[4 * ks + 2], h[4 * ks + 3], bq0 + ks * 128, ks != 0);
                WG_COMMIT();
                WG_WAIT(1);
                reg_fence<28>(av);
#pragma unroll
                for (int g = 0; g < 7; g++) {
                    vp[2 * g] = pack2(av[4 * g], av[4 * g + 1]); vp[2 * g + 1] = pack2(av[4 * g + 2], av[4 * g + 3]);
                    kvg[3584 + g * 32] = vp[2 * g]; kvg[3584 + 224 + g * 32] = vp[2 * g + 1];
                }
                warp_arrive(BAR(B_PUB + 1));
                PROFC(5);
                WG_FENCE();
#pragma unroll
                for (int ks = VPRE; ks < 28; ks++) wgmma_rl_56(aq, h[4 * ks], h[4 * ks + 1], h[4 * ks + 2], h[4 * ks + 3], bq0 + ks * 128, ks != 0);
                WG_COMMIT();
                WAIT(B_PUB + 1, 0);
                const uint32_t rg = 8 * w + 2 * wi + ((lane >> 3) & 1);
                const uint32_t ko = sb + OFF_Y + Y_KOWN + rg * 896 + (lane & 7) * 16, qo = sb + OFF_Y + Y_Q + rg * 1024 + (lane >> 4) * 128 + (lane & 7) * 16;
#pragma unroll
                for (int g = 0; g < 6; g += 2) {
                    stsm4(ko + (g + (lane >> 4)) * 128, kp[2 * g], kp[2 * g + 1], kp[2 * g + 2], kp[2 * g + 3]);
                    stsm4(ko + (Y_VOWN - Y_KOWN) + (g + (lane >> 4)) * 128, vp[2 * g], vp[2 * g + 1], vp[2 * g + 2], vp[2 * g + 3]);
                }
                stsm4(ko + (lane >> 4) * (Y_VOWN - Y_KOWN) + 6 * 128, kp[12], kp[13], vp[12], vp[13]);
                WG_WAIT(0);
                reg_fence<28>(aq);
                __syncwarp();
                if (lane < 3 && w == 1) mbar_arrive(BAR(B_EMPTY + lane));
                uint32_t qp[14];
#pragma unroll
                for (int i = 0; i < 14; i++) qp[i] = pack2(aq[2 * i], aq[2 * i + 1]);
                stsm4(qo, qp[0], qp[1], qp[2], qp[3]);
                stsm4(qo + 256, qp[4], qp[5], q < 2 ? qp[6] : 0u, q < 2 ? qp[7] : 0u);
                stsm4(qo + 512, q < 2 ? 0u : qp[6], q < 2 ? 0u : qp[7], qp[8], qp[9]);
                stsm4(qo + 768, qp[10], qp[11], qp[12], qp[13]);
                fence_async_smem();
                if (w == 0) { bar_arrive(4, 256); bar_sync(1, 128); } else { bar_arrive(5, 256); bar_sync(4, 256); }
            }
        }
        PROFC(6);
        WAIT(B_KRFULL, 0);
        PROFC(7);
        {
#pragma unroll 1
            for (int hf = 0; hf < 2; hf++) {
                COORDS
                if (hf > w) bar_sync(5, 256);
                float s[160];
                const float CS = 0.18898223650461361f * 1.4426950408889634f;
                const float NEG = __int_as_float(0xFF800000);
                constexpr uint64_t DQ = dconst(128, 1024, 0), DK = dconst(128, 896, 0);
                {
                    const uint32_t qd = mkdesc(sb + OFF_Y + Y_Q + hf * 8192 + w * 512, DQ), kd = mkdesc(sb + OFF_Y + Y_K + hf * 8 * 896 + w * 384, DK);
                    reg_def<160>(s);
                    WG_FENCE();
                    wgmma_sk_160<DQ, DK>(s, qd, kd, 0);
                    wgmma_sk_160<DQ, DK>(s, qd + 16, kd + 16, 1);
                    wgmma_sk_160<DQ, DK>(s + 80, qd, kd + 20 * 56, 0);
                    wgmma_sk_160<DQ, DK>(s + 80, qd + 16, kd + 20 * 56 + 16, 1);
                    WG_COMMIT();
                    WG_WAIT(0);
                    reg_fence<160>(s);
                }
                if (r < 2) {
                    const int pmin = 4 - 2 * r - hf;
#pragma unroll
                    for (int p4 = 0; p4 < 4; p4++)
                        if (p4 < pmin) {
#pragma unroll
                            for (int i = 0; i < 32; i++) asm volatile("mov.b32 %0, 0xFF800000;" : "=f"(s[32 * p4 + i]));
                        }
                }
                const bool c0 = 2 * q > lr, c1 = 2 * q + 1 > lr;
#pragma unroll
                for (int pp = 0; pp < 4; pp++) {
                    const bool me = pp == wi;
                    float* e = s + 8 * pp;
                    if (me && !c0) { e[0] = NEG; e[6] = NEG; }
                    if (me && !c1) { e[1] = NEG; e[7] = NEG; }
                    if (me) { e[2] = NEG; e[3] = NEG; }
                    e = s + 8 * (pp + 16);
                    if (me && c0) { e[0] = NEG; e[6] = NEG; }
                    if (me && c1) { e[1] = NEG; e[7] = NEG; }
                    if (me) { e[4] = NEG; e[5] = NEG; }
                }
#pragma unroll
                for (int i = 0; i < 24; i++) s[i] = (i >> 3) < wi ? s[136 + i] : s[i];
                int i0 = 0x80000000, i1 = 0x80000000, i2 = 0x80000000, i3 = 0x80000000;
#pragma unroll
                for (int pp = 0; pp < 17; pp++) {
                    const float* e = s + 8 * pp;
                    i0 = __vimax3_s32(i0, __float_as_int(e[0]), __float_as_int(e[1])); i1 = __vimax3_s32(i1, __float_as_int(e[2]), __float_as_int(e[3]));
                    i2 = __vimax3_s32(i2, __float_as_int(e[4]), __float_as_int(e[5])); i3 = __vimax3_s32(i3, __float_as_int(e[6]), __float_as_int(e[7]));
                }
                i0 = max(i0, i2); i1 = max(i1, i3);
                i0 = max(i0, __shfl_xor_sync(~0u, i0, 1)); i1 = max(i1, __shfl_xor_sync(~0u, i1, 1));
                i0 = max(i0, __shfl_xor_sync(~0u, i0, 2)); i1 = max(i1, __shfl_xor_sync(~0u, i1, 2));
                if (__any_sync(~0u, (i0 | i1) < 0)) {
                    uint32_t u0 = ~0u, u1 = ~0u, u2 = ~0u, u3 = ~0u;
#pragma unroll
                    for (int pp = 0; pp < 17; pp++) {
                        const float* e = s + 8 * pp;
                        u0 = __vimin3_u32(u0, __float_as_uint(e[0]), __float_as_uint(e[1])); u1 = __vimin3_u32(u1, __float_as_uint(e[2]), __float_as_uint(e[3]));
                        u2 = __vimin3_u32(u2, __float_as_uint(e[4]), __float_as_uint(e[5])); u3 = __vimin3_u32(u3, __float_as_uint(e[6]), __float_as_uint(e[7]));
                    }
                    u0 = min(u0, u2); u1 = min(u1, u3);
                    u0 = min(u0, __shfl_xor_sync(~0u, u0, 1)); u1 = min(u1, __shfl_xor_sync(~0u, u1, 1));
                    u0 = min(u0, __shfl_xor_sync(~0u, u0, 2)); u1 = min(u1, __shfl_xor_sync(~0u, u1, 2));
                    if (i0 < 0) i0 = u0;
                    if (i1 < 0) i1 = u1;
                }
                const float ma = __int_as_float(i0), mb = __int_as_float(i1);
                const float na = -ma * CS, nb = -mb * CS;
                PROFC(8 + 3 * hf);
                {
                    WAIT(B_VRFULL, 0);
                    float o[16] = {}, rs[4] = {};
                    const uint32_t va = sb + OFF_Y + Y_VR + (8 * hf + ((lane >> 3) & 1)) * 896 + (3 * w + (lane >> 4)) * 128 + (lane & 7) * 16;
                    constexpr uint32_t OWN = Y_VOWN - 32 * 896;
#pragma unroll
                    for (int pp = 0; pp < 17; pp++) {
                        uint32_t B[8];
                        const uint32_t v = va + pp * 1792 + (pp < 3 ? (pp < wi ? 17 * 1792 + OWN : 0) : pp == 16 ? OWN : pp >= 12 ? hf * OWN : 0);
                        ldsm4t(v, B); ldsm4t(v + 256, B + 4);
                        float e[8];
#pragma unroll
                        for (int i = 0; i < 8; i++) e[i] = ex2(fmaf(s[8 * pp + i], CS, (i & 2) ? nb : na));
                        const uint32_t p0 = pack2(e[0], e[1]), p1 = pack2(e[2], e[3]), p2 = pack2(e[4], e[5]), p3 = pack2(e[6], e[7]);
                        mma16816(rs, p0, p1, p2, p3, 0x3F803F80u, 0x3F803F80u);
#pragma unroll
                        for (int g = 0; g < 4; g++) mma16816(o + 4 * g, p0, p1, p2, p3, B[2 * g], B[2 * g + 1]);
                    }
                    PROFC(9 + 3 * hf);
                    const float ia = rcp(rs[0]), ib = rcp(rs[2]);
                    uint32_t* og = act + RB_O + hf * 14336 + (7 * j + 3 * w) * 256 + wi * 64 + lane;
#pragma unroll
                    for (int g = 0; g < 4; g++) {
                        if ((g == 3 - 3 * w) ? ((q >> 1) == w) : true) {
                            og[g * 256] = pack2(o[4 * g] * ia, o[4 * g + 1] * ia);
                            og[g * 256 + 32] = pack2(o[4 * g + 2] * ib, o[4 * g + 3] * ib);
                        }
                    }
                    warp_arrive(BAR(B_PUB + 2 + hf));
                    PROFC(10 + 3 * hf);
                }
            }
        }
        uint32_t x1p[14];
        COORDS
        constexpr uint64_t DT = dconst(1024, 128, 0);
        const int tile = opaque((lds1(sb + M_EPOCH) & 1) * 2 + w);
        {
            float ac[28];
            const uint32_t ad = mkdesc(sb + (w ? OFF_Y + HALF : OFF_X), DT), bd = mkdesc(sb + OFF_X + HALF, DB128) + kh;
            WAIT(B_WOFULL, 0);
            WAIT(B_MOD1, 1);
            WAIT(B_GFULL + w, 0);
            PROFC(28);
            reg_def<28>(ac);
#pragma unroll 1
            for (int u = 0; u < 4; u++) {
                if (u == 2) WAIT(B_XFULL + 2 + w, 1);
                WG_FENCE();
#pragma unroll
                for (int i = 0; i < 7; i++) wgmma_ss_56<DT, DB128>(ac, ad + (7 * u + i) * 128, bd + (7 * u + i) * 128, (u | i) != 0);
            }
            WG_COMMIT();
            WG_WAIT(0);
            reg_fence<28>(ac);
            PROFC(14);
            __syncwarp();
            if (lane < 3) mbar_arrive(BAR(B_EMPTY + 4 - w + lane));
            if (lane < 3 && w == 0) mbar_arrive(BAR(B_EMPTY + lane));
            float ds[4] = {}, da[4] = {}, db[4] = {};
            uint32_t* xo = act + RB_X1 + tile * 14336 + 7 * j * 256 + wi * 64 + lane;
#pragma unroll
            for (int g = 0; g < 7; g++) {
                const float2 ga = *(const float2*)(smem + M_G + (8 * g + 2 * q) * 4);
                x1p[2 * g] = pack2(fmaf(ga.x, ac[4 * g], bf_lo(xr[2 * g])), fmaf(ga.y, ac[4 * g + 1], bf_hi(xr[2 * g])));
                x1p[2 * g + 1] = pack2(fmaf(ga.x, ac[4 * g + 2], bf_lo(xr[2 * g + 1])), fmaf(ga.y, ac[4 * g + 3], bf_hi(xr[2 * g + 1])));
                st_relaxed(xo + g * 256, nz(x1p[2 * g])); st_relaxed(xo + g * 256 + 32, nz(x1p[2 * g + 1]));
                mma1688(ds, x1p[2 * g], x1p[2 * g + 1], 0x3F803F80u);
                mma1688(da, x1p[2 * g], x1p[2 * g + 1], x1p[2 * g]);
                mma1688(db, x1p[2 * g], x1p[2 * g + 1], x1p[2 * g + 1]);
            }
            const int src = (lane & ~3) | (lr >> 1);
            const float qa = __shfl_sync(~0u, (lr & 1) ? da[1] : da[0], src), qb = __shfl_sync(~0u, (lr & 1) ? db[3] : db[2], src);
            const float kk = (q & 1) ? ((q & 2) ? qb : qa) : ((q & 2) ? ds[2] : ds[0]);
            st_relaxed(act + RB_ST + ((tile * 8 + j) * 64 + 16 * wi + lr + 4 * (q & 2)) * 2 + (q & 1), nz(__float_as_uint(kk)));
            __syncwarp();
            if (lane < 2) mbar_arrive(BAR(B_PUB + 4 + w));
        }
        PROFC(15);
        uint32_t h2a[32], h2b[24];
        {
            const int fa = pass_f(fs, 0), fb = pass_f(fs, 1), fc = pass_f(fs, 2);
            uint32_t* h2g = act + RB_H2 + (8 * w + 2 * wi) * 32 + lane;
            const uint32_t a0 = mkdesc(sb + OFF_Y + w * HALF, DT);
            {
                LnRow ca, cb;
                {
                    const uint32_t* sg = act + RB_ST + ((tile * 8 + 2 * q) * 64 + 16 * wi + lr) * 2;
                    uint2 u[4];
                    WAIT(B_FULLV + w, 1);
                    PROFC(16);
#pragma unroll
                    for (int i = 0; i < 4; i++) { const float2 v = lds2f(sb + OFF_X + X_STAT + w * 49152 + ((2 * q + (i >> 1)) * 64 + 16 * wi + lr + 8 * (i & 1)) * 8); u[i] = make_uint2(__float_as_uint(v.x), __float_as_uint(v.y)); }
                    while (__any_sync(~0u, min(min(min(u[0].x, u[0].y), min(u[1].x, u[1].y)), min(min(u[2].x, u[2].y), min(u[3].x, u[3].y))) == 0u)) {
#pragma unroll
                        for (int i = 0; i < 4; i++) u[i] = ld_relaxed2(sg + (i >> 1) * 128 + (i & 1) * 16);
                    }
                    warp_arrive(BAR(B_EMPTY + 3 + 3 * w));
                    float v[4] = {__uint_as_float(u[0].x) + __uint_as_float(u[2].x), __uint_as_float(u[0].y) + __uint_as_float(u[2].y),
                                  __uint_as_float(u[1].x) + __uint_as_float(u[3].x), __uint_as_float(u[1].y) + __uint_as_float(u[3].y)};
#pragma unroll
                    for (int i = 0; i < 4; i++) { v[i] += __shfl_xor_sync(~0u, v[i], 1); v[i] += __shfl_xor_sync(~0u, v[i], 2); }
                    ca = ln_coeffs(v[0] * (1.f / DM), v[1] * (1.f / DM));
                    cb = ln_coeffs(v[2] * (1.f / DM), v[3] * (1.f / DM));
                }
                const uint32_t ha = sb + OFF_Y + w * HALF + (lane >> 4) * 1024 + (2 * wi + ((lane >> 3) & 1)) * 128 + (lane & 7) * 16;
                const uint32_t sta = sb + M_ST + q * 16;
                const uint32_t* xg = act + RB_X1 + tile * 14336 + (lane >> 4) * 256 + wi * 64 + (lane & 15) * 4;
                uint32_t x[8];
                const uint32_t xs = sb + OFF_Y + w * HALF + (lane >> 4) * 1024 + wi * 256 + (lane & 15) * 16;
                uint4 st[2];
                auto load = [&](int s) {
                    if (s == 4) mbar_wait_c(BAR(B_XFULL + 4 + w), 1);
                    ldsm4(ha + s * 4096, x); ldsm4(ha + s * 4096 + 2048, x + 4);
                    st[0] = lds4(sta + s * 128); st[1] = lds4(sta + s * 128 + 64);
                };
                auto prep = [&](int s, uint32_t* f) {
                    if (__any_sync(~0u, min(min(min(x[0], x[1]), min(x[2], x[3])), min(min(x[4], x[5]), min(x[6], x[7]))) == 0u)) {
                        WG_WAIT(0);
                        x1_fix(xg, xs, s);
                        ldsm4(ha + s * 4096, x); ldsm4(ha + s * 4096 + 2048, x + 4);
                    }
#pragma unroll
                    for (int i = 0; i < 2; i++) {
                        f[4 * i] = ln_mod(ln_norm(x[4 * i], ca), st[i].x, st[i].y); f[4 * i + 1] = ln_mod(ln_norm(x[4 * i + 1], cb), st[i].x, st[i].y);
                        f[4 * i + 2] = ln_mod(ln_norm(x[4 * i + 2], ca), st[i].z, st[i].w); f[4 * i + 3] = ln_mod(ln_norm(x[4 * i + 3], cb), st[i].z, st[i].w);
                    }
                    if (s < 13) load(s + 1);
                    stsm4(ha + s * 4096, f[0], f[1], f[2], f[3]); stsm4(ha + s * 4096 + 2048, f[4], f[5], f[6], f[7]);
                };
                float ac[128];
                uint32_t fr[3][8];
                uint64_t bd = (DB128 & ~0xFFFFFFFFull) | mkdesc(sb, DB128);
                reg_def<128>(ac);
                WAIT(B_GFULL + 2 + w, 0);
                load(0);
                prep(0, fr[0]);
                PROFC(17);
#pragma unroll
                for (int s = 0; s < 14; s++) {
                    const uint32_t* f = fr[s % 3];
                    WAIT(B_FULL + g1_slot(s), s >= 7);
                    WG_FENCE();
                    wgmma_rl_256(ac, f[0], f[1], f[2], f[3], bd, s != 0);
                    wgmma_rl_256(ac, f[4], f[5], f[6], f[7], bd + 128, 1);
                    bd += s == 6 ? p.zero - 6 * 1024ull : 1024;
                    WG_COMMIT();
                    if (s < 13) prep(s + 1, fr[(s + 1) % 3]);
                    if (s > 0) { WG_WAIT(1); warp_arrive(BAR(B_EMPTY + g1_slot(s - 1))); }
                }
                fence_async_smem();
                PROFC(18);
                WG_WAIT(0);
                reg_fence<128>(ac);
                warp_arrive(BAR(B_EMPTY + 6));
#pragma unroll
                for (int g = 0; g < 16; g++) {
                    h2a[2 * g] = hmul2(pack2_relu(ac[4 * g], ac[4 * g + 1]), pack2(ac[64 + 4 * g], ac[64 + 4 * g + 1]));
                    h2a[2 * g + 1] = hmul2(pack2_relu(ac[4 * g + 2], ac[4 * g + 3]), pack2(ac[64 + 4 * g + 2], ac[64 + 4 * g + 3]));
                }
                bar_sync(1 + w, 128);
            }
            PROFC(19);
            {
                float ac[64];
                reg_def<64>(ac);
                const uint32_t bx = mkdesc(sb, dconst(8192, 1024, 1));
#pragma unroll 1
                for (int s = 0; s < 7; s++) {
                    WAIT(B_FULL + s, 0);
                    const uint32_t ad = a0 + s * 512, bd = bx + (slot_off(s) >> 4);
                    WG_FENCE();
#pragma unroll
                    for (int k = 0; k < 4; k++) wgmma_ss_128<DT, DB128>(ac, ad + k * 128, bd + k * 128, (s | k) != 0);
                    WG_COMMIT();
                    if (s == 1) {
#pragma unroll
                        for (int g = 0; g < 16; g++) { h2g[(fa / 8 + g) * 512] = h2a[2 * g]; h2g[(fa / 8 + g) * 512 + 32] = h2a[2 * g + 1]; }
                        warp_arrive(BAR(B_PUB + 6));
                    }
                    if (s > 0) { WG_WAIT(1); warp_arrive(BAR(B_EMPTY + s - 1)); }
                }
                WG_WAIT(0);
                reg_fence<64>(ac);
                warp_arrive(BAR(B_EMPTY + 6));
#pragma unroll
                for (int g = 0; g < 8; g++) {
                    h2b[2 * g] = hmul2(pack2_relu(ac[4 * g], ac[4 * g + 1]), pack2(ac[32 + 4 * g], ac[32 + 4 * g + 1]));
                    h2b[2 * g + 1] = hmul2(pack2_relu(ac[4 * g + 2], ac[4 * g + 3]), pack2(ac[32 + 4 * g + 2], ac[32 + 4 * g + 3]));
                }
            }
            PROFC(27);
            {
                float ac[32];
                reg_def<32>(ac);
                const uint32_t bx = mkdesc(sb, dconst(4096, 512, 2));
#pragma unroll 1
                for (int s = 0; s < 7; s++) {
                    WAIT(B_FULL + s, 1);
                    const uint32_t ad = a0 + s * 512, bd = bx + (slot_off(s) >> 4);
                    WG_FENCE();
#pragma unroll
                    for (int k = 0; k < 4; k++) wgmma_ss_64<DT, dconst(4096, 512, 2)>(ac, ad + k * 128, bd + k * 64, (s | k) != 0);
                    WG_COMMIT();
                    if (s == 1) {
#pragma unroll
                        for (int g = 0; g < 8; g++) { h2g[(fb / 8 + g) * 512] = h2b[2 * g]; h2g[(fb / 8 + g) * 512 + 32] = h2b[2 * g + 1]; }
                        warp_arrive(BAR(B_PUB + 7));
                    }
                    if (s > 0) { WG_WAIT(1); warp_arrive(BAR(B_EMPTY + s - 1)); }
                }
                WG_WAIT(0);
                reg_fence<32>(ac);
                __syncwarp();
                if (lane < 6) mbar_arrive(BAR(B_EMPTY + 6 + lane));
                PROFC(20);
#pragma unroll
                for (int g = 0; g < 4; g++) {
                    h2b[16 + 2 * g] = hmul2(pack2_relu(ac[4 * g], ac[4 * g + 1]), pack2(ac[16 + 4 * g], ac[16 + 4 * g + 1]));
                    h2b[16 + 2 * g + 1] = hmul2(pack2_relu(ac[4 * g + 2], ac[4 * g + 3]), pack2(ac[16 + 4 * g + 2], ac[16 + 4 * g + 3]));
                    h2g[(fc / 8 + g) * 512] = h2b[16 + 2 * g]; h2g[(fc / 8 + g) * 512 + 32] = h2b[16 + 2 * g + 1];
                }
                warp_arrive(BAR(B_PUB + 8));
                asm volatile("barrier.cluster.wait.aligned;" ::: "memory");
                if (lane == 0) {
                    uint32_t rb;
                    asm volatile("mapa.shared::cluster.u32 %0, %1, %2;" : "=r"(rb) : "r"(BAR(B_PEER)), "r"(kh ^ 1));
                    asm volatile("mbarrier.arrive.relaxed.cluster.shared::cluster.b64 _, [%0];" ::"r"(rb) : "memory");
                }
            }
        }
        PROFC(21);
        {
            float ac[56];
            reg_def<56>(ac);
            constexpr uint64_t DAN = dconst(2048, 128, 0);
            constexpr uint64_t DW = dconst(128, 512, 0);
            const uint32_t bx = mkdesc(sb, DW);
#pragma unroll
            for (int e = 0; e < 4; e++) {
                WAIT(B_FULL + e, 0);
                const uint64_t bd = ((DW & ~0xFFFFFFFFull) | bx) + (slot_off(e) >> 4);
                const uint32_t* hh = e < 2 ? h2a + 16 * e : h2b + 16 * (e - 2);
                WG_FENCE();
#pragma unroll
                for (int k = 0; k < (e < 3 ? 4 : 2); k++) wgmma_rl_112(ac, hh[4 * k], hh[4 * k + 1], hh[4 * k + 2], hh[4 * k + 3], bd + (k >> 1) * 512 + (k & 1) * 16, (e | k) != 0);
                WG_COMMIT();
                if (e > 0) { WG_WAIT(1); warp_arrive(BAR(B_EMPTY + e - 1)); }
            }
            PROFC(22);
            uint32_t ad = mkdesc(sb + 4 * 16384 + 8192 + w * 1024, DAN), bd = bx + 4 * 1024, fb_ = BAR(B_FULL + 4), eb_ = BAR(B_EMPTY + 3), par = 0;
#pragma unroll 1
            for (int e = 4; e < 25; e++) {
                mbar_wait_c(fb_, par);
                WG_FENCE();
                wgmma_ss_112<DAN, DW>(ac, ad, bd, 1);
                wgmma_ss_112<DAN, DW>(ac, ad + 256, bd + 16, 1);
                WG_COMMIT();
                WG_WAIT(1);
                warp_arrive(eb_);
                eb_ = fb_ + 8 * (B_EMPTY - B_FULL);
                ad += 1024; bd += 1024; fb_ += 8;
                if (e == 11 || e == 23) { ad -= 12 * 1024; bd -= 12 * 1024; fb_ -= 96; par ^= 1; }
            }
            mbar_wait_cluster(BAR(B_PEER), 0);
            WG_WAIT(0);
            reg_fence<56>(ac);
            PROFC(24);
            uint32_t rdst, rbar;
            asm volatile("mapa.shared::cluster.u32 %0, %1, %2;" : "=r"(rdst) : "r"(sb + OFF_Y + (5 + w) * 16384 + t * 16), "r"(kh ^ 1));
            asm volatile("mapa.shared::cluster.u32 %0, %1, %2;" : "=r"(rbar) : "r"(BAR(B_XCH + w)), "r"(kh ^ 1));
#pragma unroll
            for (int g = 0; g < 3; g++)
                asm volatile("st.async.shared::cluster.mbarrier::complete_tx::bytes.v4.b32 [%0], {%1,%2,%3,%4}, [%5];" ::"r"(rdst + g * 2048),
                             "r"(pack2(ac[28 + 8 * g], ac[29 + 8 * g])), "r"(pack2(ac[30 + 8 * g], ac[31 + 8 * g])), "r"(pack2(ac[32 + 8 * g], ac[33 + 8 * g])),
                             "r"(pack2(ac[34 + 8 * g], ac[35 + 8 * g])), "r"(rbar) : "memory");
            asm volatile("st.async.shared::cluster.mbarrier::complete_tx::bytes.v2.b32 [%0], {%1,%2}, [%3];" ::"r"(rdst + 6144 - t * 8),
                         "r"(pack2(ac[52], ac[53])), "r"(pack2(ac[54], ac[55])), "r"(rbar) : "memory");
            mbar_wait_cluster(BAR(B_XCH + w), 0);
            PROFC(25);
            uint32_t op[14], rv[14];
#pragma unroll
            for (int g = 0; g < 3; g++) *(uint4*)(rv + 4 * g) = *(const uint4*)(smem + OFF_Y + (5 + w) * 16384 + t * 16 + g * 2048);
            *(uint2*)(rv + 12) = *(const uint2*)(smem + OFF_Y + (5 + w) * 16384 + 6144 + t * 8);
#pragma unroll
            for (int i = 0; i < 14; i++) {
                const float2 gb = *(const float2*)(smem + M_G + 224 + (8 * (i >> 1) + 2 * q) * 4);
                op[i] = pack2(fmaf(gb.x, ac[2 * i] + bf_lo(rv[i]), bf_lo(x1p[i])), fmaf(gb.y, ac[2 * i + 1] + bf_hi(rv[i]), bf_hi(x1p[i])));
            }
            WAIT(B_EMPTY + 1, 0);
            const uint32_t oc = sb + OUT_STAGE + warp * 1792;
            const uint32_t oa = oc + (((lane >> 3) & 1) * 8 + (lane & 7)) * 112 + (lane >> 4) * 16;
            stsm4(oa, op[0], op[1], op[2], op[3]); stsm4(oa + 32, op[4], op[5], op[6], op[7]); stsm4(oa + 64, op[8], op[9], op[10], op[11]);
            asm volatile("stmatrix.sync.aligned.m8n8.x2.shared.b16 [%0], {%1,%2};" ::"r"(oa + 96), "r"(op[12]), "r"(op[13]));
            fence_async_smem();
            __syncwarp();
            asm volatile("{\n.reg .pred p;\nelect.sync _|p, 0xffffffff;\n@p cp.async.bulk.tensor.3d.global.shared::cta.bulk_group [%0, {%2, %3, %4}], [%1];\n"
                         "cp.async.bulk.commit_group;\ncp.async.bulk.wait_group.read 0;\n}" ::"l"(&p.om), "r"(oc), "r"(56 * j), "r"(128 * r + 64 * w + 16 * wi), "r"(0) : "memory");
        }
        PROFC(26);
        bar_sync(1 + w, 128);
        if (wi == 0) warp_arrive(BAR(B_DONE));
        return;
    }
    helper_late(p, r, j, warp PROF_ARGS);
}

#undef act
typedef CUresult (*EncodeFn)(CUtensorMap*, CUtensorMapDataType, cuuint32_t, void*, const cuuint64_t*, const cuuint64_t*, const cuuint32_t*,
                             const cuuint32_t*, CUtensorMapInterleave, CUtensorMapSwizzle, CUtensorMapL2promotion, CUtensorMapFloatOOBfill);

static void make_map(EncodeFn fn, CUtensorMap* m, const void* ptr, uint64_t d0, uint64_t d1, uint64_t d2, uint64_t s1, uint64_t s2,
                     uint32_t b0, uint32_t b1, uint32_t b2, CUtensorMapSwizzle sw) {
    cuuint64_t dims[3] = {d0, d1, d2}, strides[2] = {s1, s2};
    cuuint32_t box[3] = {b0, b1, b2}, es[3] = {1, 1, 1};
    CUresult rc = fn(m, CU_TENSOR_MAP_DATA_TYPE_BFLOAT16, 3, (void*)ptr, dims, strides, box, es, CU_TENSOR_MAP_INTERLEAVE_NONE, sw,
                     CU_TENSOR_MAP_L2_PROMOTION_L2_128B, CU_TENSOR_MAP_FLOAT_OOB_FILL_NONE);
    (void)rc;
}

extern "C" void kernel_launch(void* const* d_in, const int* in_sizes, int n_in, void* d_out, int out_size) {
    (void)in_sizes; (void)n_in; (void)out_size;
    static EncodeFn fn = nullptr;
    static uint32_t* act_base = nullptr;
    if (!fn) {
        cudaDriverEntryPointQueryResult st;
        cudaGetDriverEntryPoint("cuTensorMapEncodeTiled", (void**)&fn, cudaEnableDefault, &st);
        void* a = nullptr;
        cudaGetSymbolAddress(&a, g_act);
        act_base = (uint32_t*)(((uintptr_t)a + 0xFFFFF) & ~(uintptr_t)0xFFFFF);
        cudaFuncSetAttribute(fused_block_kernel, cudaFuncAttributeMaxDynamicSharedMemorySize, SMEM_BYTES);
    }
    Params p;
    p.x = (const bf16*)d_in[0];
    const bf16* wqkv = (const bf16*)d_in[1];
    p.wqkv = wqkv;
    p.wop = (const bf16*)d_in[2];
    p.wg = (const bf16*)d_in[4];
    p.wu = (const bf16*)d_in[5];
    p.wd = (const bf16*)d_in[6];
    p.c = (const bf16*)d_in[7];
    p.wmod = (const bf16*)d_in[8];
    p.out = (bf16*)d_out;
    p.zero = 0;
    p.actb = act_base;
    make_map(fn, &p.wm, p.wmod, 2688, 448, 1, 5376, 5376 * 448, 16, 224, 1, CU_TENSOR_MAP_SWIZZLE_NONE);
    make_map(fn, &p.wm2, p.wmod, 2688, 448, 1, 5376, 5376 * 448, 32, 224, 1, CU_TENSOR_MAP_SWIZZLE_NONE);
    make_map(fn, &p.om, p.out, 448, 2048, 1, 896, 896 * 2048, 56, 16, 1, CU_TENSOR_MAP_SWIZZLE_NONE);
    make_map(fn, &p.xm, p.x, 448, 2048, 1, 896, 896 * 2048, 64, 128, 1, CU_TENSOR_MAP_SWIZZLE_128B);
    make_map(fn, &p.qkv, wqkv, 1344, 448, 1, 2688, 2688 * 448, 64, 224, 1, CU_TENSOR_MAP_SWIZZLE_128B);
    make_map(fn, &p.wo, p.wop, 448, 448, 1, 896, 896 * 448, 64, 224, 1, CU_TENSOR_MAP_SWIZZLE_128B);
    make_map(fn, &p.ga, p.wg, 64, 448, 28, 3584, 128, 64, 32, 2, CU_TENSOR_MAP_SWIZZLE_128B);
    make_map(fn, &p.ua, p.wu, 64, 448, 28, 3584, 128, 64, 32, 2, CU_TENSOR_MAP_SWIZZLE_128B);
    make_map(fn, &p.gb, p.wg, 64, 448, 28, 3584, 128, 64, 64, 1, CU_TENSOR_MAP_SWIZZLE_128B);
    make_map(fn, &p.ub, p.wu, 64, 448, 28, 3584, 128, 64, 64, 1, CU_TENSOR_MAP_SWIZZLE_128B);
    make_map(fn, &p.gc, p.wg, 32, 448, 56, 3584, 64, 32, 64, 1, CU_TENSOR_MAP_SWIZZLE_64B);
    make_map(fn, &p.uc, p.wu, 32, 448, 56, 3584, 64, 32, 64, 1, CU_TENSOR_MAP_SWIZZLE_64B);
    make_map(fn, &p.dn, p.wd, 8, 1792, 56, 896, 16, 8, 32, 7, CU_TENSOR_MAP_SWIZZLE_NONE);
    fused_block_kernel<<<NCTA, 384, SMEM_BYTES>>>(p);
}
```

```cpp
#include <cuda_runtime.h>
#include <cuda_bf16.h>
#include <cuda.h>
#include <stdint.h>

typedef __nv_bfloat16 bf16;

template<uint64_t CA, uint64_t CB> __device__ __forceinline__ void wgmma_sk_160(float* d, uint32_t da, uint32_t db, int sd) {
  asm volatile("{\n.reg .pred p;\n.reg .b64 a, b;\nsetp.ne.b32 p, %82, 0;\nmov.b64 a, {%80, %83};\nmov.b64 b, {%81, %84};\n"
    "wgmma.mma_async.sync.aligned.m64n160k16.f32.bf16.bf16 {%0,%1,%2,%3,%4,%5,%6,%7,%8,%9,%10,%11,%12,%13,%14,%15,%16,%17,%18,%19,%20,%21,%22,%23,%24,%25,%26,%27,%28,%29,%30,%31,%32,%33,%34,%35,%36,%37,%38,%39,%40,%41,%42,%43,%44,%45,%46,%47,%48,%49,%50,%51,%52,%53,%54,%55,%56,%57,%58,%59,%60,%61,%62,%63,%64,%65,%66,%67,%68,%69,%70,%71,%72,%73,%74,%75,%76,%77,%78,%79}, a, b, p, 1, 1, 0, 0;\n}\n"
    : "+f"(d[0]),"+f"(d[1]),"+f"(d[2]),"+f"(d[3]),"+f"(d[4]),"+f"(d[5]),"+f"(d[6]),"+f"(d[7]),"+f"(d[8]),"+f"(d[9]),"+f"(d[10]),"+f"(d[11]),"+f"(d[12]),"+f"(d[13]),"+f"(d[14]),"+f"(d[15]),"+f"(d[16]),"+f"(d[17]),"+f"(d[18]),"+f"(d[19]),"+f"(d[20]),"+f"(d[21]),"+f"(d[22]),"+f"(d[23]),"+f"(d[24]),"+f"(d[25]),"+f"(d[26]),"+f"(d[27]),"+f"(d[28]),"+f"(d[29]),"+f"(d[30]),"+f"(d[31]),"+f"(d[32]),"+f"(d[33]),"+f"(d[34]),"+f"(d[35]),"+f"(d[36]),"+f"(d[37]),"+f"(d[38]),"+f"(d[39]),"+f"(d[40]),"+f"(d[41]),"+f"(d[42]),"+f"(d[43]),"+f"(d[44]),"+f"(d[45]),"+f"(d[46]),"+f"(d[47]),"+f"(d[48]),"+f"(d[49]),"+f"(d[50]),"+f"(d[51]),"+f"(d[52]),"+f"(d[53]),"+f"(d[54]),"+f"(d[55]),"+f"(d[56]),"+f"(d[57]),"+f"(d[58]),"+f"(d[59]),"+f"(d[60]),"+f"(d[61]),"+f"(d[62]),"+f"(d[63]),"+f"(d[64]),"+f"(d[65]),"+f"(d[66]),"+f"(d[67]),"+f"(d[68]),"+f"(d[69]),"+f"(d[70]),"+f"(d[71]),"+f"(d[72]),"+f"(d[73]),"+f"(d[74]),"+f"(d[75]),"+f"(d[76]),"+f"(d[77]),"+f"(d[78]),"+f"(d[79])
    : "r"(da), "r"(db), "r"(sd), "n"((uint32_t)(CA >> 32)), "n"((uint32_t)(CB >> 32)));
}
__device__ __forceinline__ void wgmma_rl_56(float* d, uint32_t a0, uint32_t a1, uint32_t a2, uint32_t a3, uint64_t db, int sd) {
  asm volatile("{\n.reg .pred p;\nsetp.ne.b32 p, %33, 0;\n"
    "wgmma.mma_async.sync.aligned.m64n56k16.f32.bf16.bf16 {%0,%1,%2,%3,%4,%5,%6,%7,%8,%9,%10,%11,%12,%13,%14,%15,%16,%17,%18,%19,%20,%21,%22,%23,%24,%25,%26,%27}, {%28,%29,%30,%31}, %32, p, 1, 1, 1;\n}\n"
    : "+f"(d[0]),"+f"(d[1]),"+f"(d[2]),"+f"(d[3]),"+f"(d[4]),"+f"(d[5]),"+f"(d[6]),"+f"(d[7]),"+f"(d[8]),"+f"(d[9]),"+f"(d[10]),"+f"(d[11]),"+f"(d[12]),"+f"(d[13]),"+f"(d[14]),"+f"(d[15]),"+f"(d[16]),"+f"(d[17]),"+f"(d[18]),"+f"(d[19]),"+f"(d[20]),"+f"(d[21]),"+f"(d[22]),"+f"(d[23]),"+f"(d[24]),"+f"(d[25]),"+f"(d[26]),"+f"(d[27])
    : "r"(a0), "r"(a1), "r"(a2), "r"(a3), "l"(db), "r"(sd));
}
template<uint64_t CA, uint64_t CB> __device__ __forceinline__ void wgmma_ss_56(float* d, uint32_t da, uint32_t db, int sd) {
  asm volatile("{\n.reg .pred p;\n.reg .b64 a, b;\nsetp.ne.b32 p, %30, 0;\nmov.b64 a, {%28, %31};\nmov.b64 b, {%29, %32};\n"
    "wgmma.mma_async.sync.aligned.m64n56k16.f32.bf16.bf16 {%0,%1,%2,%3,%4,%5,%6,%7,%8,%9,%10,%11,%12,%13,%14,%15,%16,%17,%18,%19,%20,%21,%22,%23,%24,%25,%26,%27}, a, b, p, 1, 1, 0, 1;\n}\n"
    : "+f"(d[0]),"+f"(d[1]),"+f"(d[2]),"+f"(d[3]),"+f"(d[4]),"+f"(d[5]),"+f"(d[6]),"+f"(d[7]),"+f"(d[8]),"+f"(d[9]),"+f"(d[10]),"+f"(d[11]),"+f"(d[12]),"+f"(d[13]),"+f"(d[14]),"+f"(d[15]),"+f"(d[16]),"+f"(d[17]),"+f"(d[18]),"+f"(d[19]),"+f"(d[20]),"+f"(d[21]),"+f"(d[22]),"+f"(d[23]),"+f"(d[24]),"+f"(d[25]),"+f"(d[26]),"+f"(d[27])
    : "r"(da), "r"(db), "r"(sd), "n"((uint32_t)(CA >> 32)), "n"((uint32_t)(CB >> 32)));
}
__device__ __forceinline__ void wgmma_rl_256(float* d, uint32_t a0, uint32_t a1, uint32_t a2, uint32_t a3, uint64_t db, int sd) {
  asm volatile("{\n.reg .pred p;\nsetp.ne.b32 p, %133, 0;\n"
    "wgmma.mma_async.sync.aligned.m64n256k16.f32.bf16.bf16 {%0,%1,%2,%3,%4,%5,%6,%7,%8,%9,%10,%11,%12,%13,%14,%15,%16,%17,%18,%19,%20,%21,%22,%23,%24,%25,%26,%27,%28,%29,%30,%31,%32,%33,%34,%35,%36,%37,%38,%39,%40,%41,%42,%43,%44,%45,%46,%47,%48,%49,%50,%51,%52,%53,%54,%55,%56,%57,%58,%59,%60,%61,%62,%63,%64,%65,%66,%67,%68,%69,%70,%71,%72,%73,%74,%75,%76,%77,%78,%79,%80,%81,%82,%83,%84,%85,%86,%87,%88,%89,%90,%91,%92,%93,%94,%95,%96,%97,%98,%99,%100,%101,%102,%103,%104,%105,%106,%107,%108,%109,%110,%111,%112,%113,%114,%115,%116,%117,%118,%119,%120,%121,%122,%123,%124,%125,%126,%127}, {%128,%129,%130,%131}, %132, p, 1, 1, 1;\n}\n"
    : "+f"(d[0]),"+f"(d[1]),"+f"(d[2]),"+f"(d[3]),"+f"(d[4]),"+f"(d[5]),"+f"(d[6]),"+f"(d[7]),"+f"(d[8]),"+f"(d[9]),"+f"(d[10]),"+f"(d[11]),"+f"(d[12]),"+f"(d[13]),"+f"(d[14]),"+f"(d[15]),"+f"(d[16]),"+f"(d[17]),"+f"(d[18]),"+f"(d[19]),"+f"(d[20]),"+f"(d[21]),"+f"(d[22]),"+f"(d[23]),"+f"(d[24]),"+f"(d[25]),"+f"(d[26]),"+f"(d[27]),"+f"(d[28]),"+f"(d[29]),"+f"(d[30]),"+f"(d[31]),"+f"(d[32]),"+f"(d[33]),"+f"(d[34]),"+f"(d[35]),"+f"(d[36]),"+f"(d[37]),"+f"(d[38]),"+f"(d[39]),"+f"(d[40]),"+f"(d[41]),"+f"(d[42]),"+f"(d[43]),"+f"(d[44]),"+f"(d[45]),"+f"(d[46]),"+f"(d[47]),"+f"(d[48]),"+f"(d[49]),"+f"(d[50]),"+f"(d[51]),"+f"(d[52]),"+f"(d[53]),"+f"(d[54]),"+f"(d[55]),"+f"(d[56]),"+f"(d[57]),"+f"(d[58]),"+f"(d[59]),"+f"(d[60]),"+f"(d[61]),"+f"(d[62]),"+f"(d[63]),"+f"(d[64]),"+f"(d[65]),"+f"(d[66]),"+f"(d[67]),"+f"(d[68]),"+f"(d[69]),"+f"(d[70]),"+f"(d[71]),"+f"(d[72]),"+f"(d[73]),"+f"(d[74]),"+f"(d[75]),"+f"(d[76]),"+f"(d[77]),"+f"(d[78]),"+f"(d[79]),"+f"(d[80]),"+f"(d[81]),"+f"(d[82]),"+f"(d[83]),"+f"(d[84]),"+f"(d[85]),"+f"(d[86]),"+f"(d[87]),"+f"(d[88]),"+f"(d[89]),"+f"(d[90]),"+f"(d[91]),"+f"(d[92]),"+f"(d[93]),"+f"(d[94]),"+f"(d[95]),"+f"(d[96]),"+f"(d[97]),"+f"(d[98]),"+f"(d[99]),"+f"(d[100]),"+f"(d[101]),"+f"(d[102]),"+f"(d[103]),"+f"(d[104]),"+f"(d[105]),"+f"(d[106]),"+f"(d[107]),"+f"(d[108]),"+f"(d[109]),"+f"(d[110]),"+f"(d[111]),"+f"(d[112]),"+f"(d[113]),"+f"(d[114]),"+f"(d[115]),"+f"(d[116]),"+f"(d[117]),"+f"(d[118]),"+f"(d[119]),"+f"(d[120]),"+f"(d[121]),"+f"(d[122]),"+f"(d[123]),"+f"(d[124]),"+f"(d[125]),"+f"(d[126]),"+f"(d[127])
    : "r"(a0), "r"(a1), "r"(a2), "r"(a3), "l"(db), "r"(sd));
}
template<uint64_t CA, uint64_t CB> __device__ __forceinline__ void wgmma_ss_128(float* d, uint32_t da, uint32_t db, int sd) {
  asm volatile("{\n.reg .pred p;\n.reg .b64 a, b;\nsetp.ne.b32 p, %66, 0;\nmov.b64 a, {%64, %67};\nmov.b64 b, {%65, %68};\n"
    "wgmma.mma_async.sync.aligned.m64n128k16.f32.bf16.bf16 {%0,%1,%2,%3,%4,%5,%6,%7,%8,%9,%10,%11,%12,%13,%14,%15,%16,%17,%18,%19,%20,%21,%22,%23,%24,%25,%26,%27,%28,%29,%30,%31,%32,%33,%34,%35,%36,%37,%38,%39,%40,%41,%42,%43,%44,%45,%46,%47,%48,%49,%50,%51,%52,%53,%54,%55,%56,%57,%58,%59,%60,%61,%62,%63}, a, b, p, 1, 1, 0, 1;\n}\n"
    : "+f"(d[0]),"+f"(d[1]),"+f"(d[2]),"+f"(d[3]),"+f"(d[4]),"+f"(d[5]),"+f"(d[6]),"+f"(d[7]),"+f"(d[8]),"+f"(d[9]),"+f"(d[10]),"+f"(d[11]),"+f"(d[12]),"+f"(d[13]),"+f"(d[14]),"+f"(d[15]),"+f"(d[16]),"+f"(d[17]),"+f"(d[18]),"+f"(d[19]),"+f"(d[20]),"+f"(d[21]),"+f"(d[22]),"+f"(d[23]),"+f"(d[24]),"+f"(d[25]),"+f"(d[26]),"+f"(d[27]),"+f"(d[28]),"+f"(d[29]),"+f"(d[30]),"+f"(d[31]),"+f"(d[32]),"+f"(d[33]),"+f"(d[34]),"+f"(d[35]),"+f"(d[36]),"+f"(d[37]),"+f"(d[38]),"+f"(d[39]),"+f"(d[40]),"+f"(d[41]),"+f"(d[42]),"+f"(d[43]),"+f"(d[44]),"+f"(d[45]),"+f"(d[46]),"+f"(d[47]),"+f"(d[48]),"+f"(d[49]),"+f"(d[50]),"+f"(d[51]),"+f"(d[52]),"+f"(d[53]),"+f"(d[54]),"+f"(d[55]),"+f"(d[56]),"+f"(d[57]),"+f"(d[58]),"+f"(d[59]),"+f"(d[60]),"+f"(d[61]),"+f"(d[62]),"+f"(d[63])
    : "r"(da), "r"(db), "r"(sd), "n"((uint32_t)(CA >> 32)), "n"((uint32_t)(CB >> 32)));
}
template<uint64_t CA, uint64_t CB> __device__ __forceinline__ void wgmma_ss_64(float* d, uint32_t da, uint32_t db, int sd) {
  asm volatile("{\n.reg .pred p;\n.reg .b64 a, b;\nsetp.ne.b32 p, %34, 0;\nmov.b64 a, {%32, %35};\nmov.b64 b, {%33, %36};\n"
    "wgmma.mma_async.sync.aligned.m64n64k16.f32.bf16.bf16 {%0,%1,%2,%3,%4,%5,%6,%7,%8,%9,%10,%11,%12,%13,%14,%15,%16,%17,%18,%19,%20,%21,%22,%23,%24,%25,%26,%27,%28,%29,%30,%31}, a, b, p, 1, 1, 0, 1;\n}\n"
    : "+f"(d[0]),"+f"(d[1]),"+f"(d[2]),"+f"(d[3]),"+f"(d[4]),"+f"(d[5]),"+f"(d[6]),"+f"(d[7]),"+f"(d[8]),"+f"(d[9]),"+f"(d[10]),"+f"(d[11]),"+f"(d[12]),"+f"(d[13]),"+f"(d[14]),"+f"(d[15]),"+f"(d[16]),"+f"(d[17]),"+f"(d[18]),"+f"(d[19]),"+f"(d[20]),"+f"(d[21]),"+f"(d[22]),"+f"(d[23]),"+f"(d[24]),"+f"(d[25]),"+f"(d[26]),"+f"(d[27]),"+f"(d[28]),"+f"(d[29]),"+f"(d[30]),"+f"(d[31])
    : "r"(da), "r"(db), "r"(sd), "n"((uint32_t)(CA >> 32)), "n"((uint32_t)(CB >> 32)));
}
template<uint64_t CA, uint64_t CB> __device__ __forceinline__ void wgmma_ss_112(float* d, uint32_t da, uint32_t db, int sd) {
  asm volatile("{\n.reg .pred p;\n.reg .b64 a, b;\nsetp.ne.b32 p, %58, 0;\nmov.b64 a, {%56, %59};\nmov.b64 b, {%57, %60};\n"
    "wgmma.mma_async.sync.aligned.m64n112k16.f32.bf16.bf16 {%0,%1,%2,%3,%4,%5,%6,%7,%8,%9,%10,%11,%12,%13,%14,%15,%16,%17,%18,%19,%20,%21,%22,%23,%24,%25,%26,%27,%28,%29,%30,%31,%32,%33,%34,%35,%36,%37,%38,%39,%40,%41,%42,%43,%44,%45,%46,%47,%48,%49,%50,%51,%52,%53,%54,%55}, a, b, p, 1, 1, 0, 1;\n}\n"
    : "+f"(d[0]),"+f"(d[1]),"+f"(d[2]),"+f"(d[3]),"+f"(d[4]),"+f"(d[5]),"+f"(d[6]),"+f"(d[7]),"+f"(d[8]),"+f"(d[9]),"+f"(d[10]),"+f"(d[11]),"+f"(d[12]),"+f"(d[13]),"+f"(d[14]),"+f"(d[15]),"+f"(d[16]),"+f"(d[17]),"+f"(d[18]),"+f"(d[19]),"+f"(d[20]),"+f"(d[21]),"+f"(d[22]),"+f"(d[23]),"+f"(d[24]),"+f"(d[25]),"+f"(d[26]),"+f"(d[27]),"+f"(d[28]),"+f"(d[29]),"+f"(d[30]),"+f"(d[31]),"+f"(d[32]),"+f"(d[33]),"+f"(d[34]),"+f"(d[35]),"+f"(d[36]),"+f"(d[37]),"+f"(d[38]),"+f"(d[39]),"+f"(d[40]),"+f"(d[41]),"+f"(d[42]),"+f"(d[43]),"+f"(d[44]),"+f"(d[45]),"+f"(d[46]),"+f"(d[47]),"+f"(d[48]),"+f"(d[49]),"+f"(d[50]),"+f"(d[51]),"+f"(d[52]),"+f"(d[53]),"+f"(d[54]),"+f"(d[55])
    : "r"(da), "r"(db), "r"(sd), "n"((uint32_t)(CA >> 32)), "n"((uint32_t)(CB >> 32)));
}
__device__ __forceinline__ void wgmma_rl_112(float* d, uint32_t a0, uint32_t a1, uint32_t a2, uint32_t a3, uint64_t db, int sd) {
  asm volatile("{\n.reg .pred p;\nsetp.ne.b32 p, %61, 0;\n"
    "wgmma.mma_async.sync.aligned.m64n112k16.f32.bf16.bf16 {%0,%1,%2,%3,%4,%5,%6,%7,%8,%9,%10,%11,%12,%13,%14,%15,%16,%17,%18,%19,%20,%21,%22,%23,%24,%25,%26,%27,%28,%29,%30,%31,%32,%33,%34,%35,%36,%37,%38,%39,%40,%41,%42,%43,%44,%45,%46,%47,%48,%49,%50,%51,%52,%53,%54,%55}, {%56,%57,%58,%59}, %60, p, 1, 1, 1;\n}\n"
    : "+f"(d[0]),"+f"(d[1]),"+f"(d[2]),"+f"(d[3]),"+f"(d[4]),"+f"(d[5]),"+f"(d[6]),"+f"(d[7]),"+f"(d[8]),"+f"(d[9]),"+f"(d[10]),"+f"(d[11]),"+f"(d[12]),"+f"(d[13]),"+f"(d[14]),"+f"(d[15]),"+f"(d[16]),"+f"(d[17]),"+f"(d[18]),"+f"(d[19]),"+f"(d[20]),"+f"(d[21]),"+f"(d[22]),"+f"(d[23]),"+f"(d[24]),"+f"(d[25]),"+f"(d[26]),"+f"(d[27]),"+f"(d[28]),"+f"(d[29]),"+f"(d[30]),"+f"(d[31]),"+f"(d[32]),"+f"(d[33]),"+f"(d[34]),"+f"(d[35]),"+f"(d[36]),"+f"(d[37]),"+f"(d[38]),"+f"(d[39]),"+f"(d[40]),"+f"(d[41]),"+f"(d[42]),"+f"(d[43]),"+f"(d[44]),"+f"(d[45]),"+f"(d[46]),"+f"(d[47]),"+f"(d[48]),"+f"(d[49]),"+f"(d[50]),"+f"(d[51]),"+f"(d[52]),"+f"(d[53]),"+f"(d[54]),"+f"(d[55])
    : "r"(a0), "r"(a1), "r"(a2), "r"(a3), "l"(db), "r"(sd));
}

constexpr int DM = 448;
constexpr int NCTA = 128;
#define WIN 6
#define NPRE 14
#define VPRE 3
constexpr int SPIN_LIMIT = 1 << 22;

constexpr uint32_t OFF_X = 0, OFF_Y = 114688, OFF_MISC = 229376, SMEM_BYTES = 232448;
constexpr uint32_t Y_VR = 0, Y_K = 28672, Y_KOWN = 57344, Y_VOWN = 71680, Y_Q = 86016;
constexpr uint32_t HALF = 57344;
constexpr uint32_t X_STAT = 49152;
constexpr uint32_t OUT_STAGE = 16384;
constexpr uint32_t M_BAR = OFF_MISC;
constexpr uint32_t M_ST = OFF_MISC + 512;
constexpr uint32_t M_G = OFF_MISC + 2304;
constexpr uint32_t M_EPOCH = OFF_MISC + 3040;
enum { B_XFULL = 0, B_FULLK = 7, B_FULLV = 8, B_FULLQ, B_KRFULL, B_VRFULL, B_WOFULL, B_XCH, B_MOD1 = 15, B_FULL = 16, B_WMFULL = 30,
       B_EMPTY = 32, B_XFREE = B_EMPTY + 12, B_GEMV, B_PEER,
       B_PUB = 47,
       B_WMFREE = 56, B_HRDY, B_GFULL = B_HRDY + 3, B_DONE = 31, B_DUMMY = B_GEMV };

__device__ uint32_t g_ticket;
__device__ __align__(128) uint32_t g_mod[8 * 6 * DM];
__device__ __align__(128) uint32_t g_flag[144 * 128];
constexpr int RB_WORDS = 262144, RB_KV = 0, RB_O = 57344, RB_X1 = 86016, RB_H2 = 143360, RB_ST = 258048;
__device__ __align__(128) uint32_t g_act[17 * RB_WORDS];
__device__ __align__(128) uint32_t g_wd[56 * 4 * 1792];
#define PROFH(id)
#define PROFH1(id)
#define PROFC(id)

struct alignas(64) Params {
    CUtensorMap wm, wm2, om, xm, qkv, wo, ga, ua, gb, ub, gc, uc, dn;
    const bf16 *x, *c, *wqkv, *wmod, *wg, *wu, *wd, *wop;
    bf16* out;
    uint32_t* actb;
    uint32_t zero;
};

__device__ __forceinline__ void mbar_init(uint32_t bar, int cnt) { asm volatile("mbarrier.init.shared::cta.b64 [%0], %1;" ::"r"(bar), "r"(cnt) : "memory"); }
__device__ __forceinline__ void mbar_arrive(uint32_t bar) { asm volatile("mbarrier.arrive.shared::cta.b64 _, [%0];" ::"r"(bar) : "memory"); }
__device__ __forceinline__ void mbar_wait(uint32_t bar, uint32_t parity) {
    uint32_t ok; int n = 0;
    do {
        asm volatile("{\n.reg .pred p;\nmbarrier.try_wait.parity.shared::cta.b64 p, [%1], %2;\nselp.u32 %0, 1, 0, p;\n}" : "=r"(ok) : "r"(bar), "r"(parity) : "memory");
        if (++n > SPIN_LIMIT) __trap();
    } while (!ok);
}
__device__ __forceinline__ void mbar_wait_c(uint32_t bar, uint32_t parity) {
    asm volatile("{\n.reg .pred p;\nWL:\nmbarrier.try_wait.parity.shared::cta.b64 p, [%0], %1, 0x989680;\n@!p bra WL;\n}" ::"r"(bar), "r"(parity) : "memory");
}
__device__ __forceinline__ void mbar_wait_cluster(uint32_t bar, uint32_t parity) {
    asm volatile("{\n.reg .pred p;\nWL:\nmbarrier.try_wait.parity.acquire.cluster.shared::cta.b64 p, [%0], %1, 0x989680;\n@!p bra WL;\n}" ::"r"(bar), "r"(parity) : "memory");
}
__device__ __forceinline__ void warp_arrive(uint32_t bar) {
    __syncwarp();
    asm volatile("{\n.reg .pred p;\nelect.sync _|p, 0xffffffff;\n@p mbarrier.arrive.shared::cta.b64 _, [%0];\n}" ::"r"(bar) : "memory");
}
__device__ __forceinline__ int opaque(int v) { return __shfl_sync(~0u, v, 0); }
__device__ __forceinline__ int fresh_tid() { int v; asm volatile("mov.u32 %0, %%tid.x;" : "=r"(v)); return v; }
__device__ __forceinline__ void bar_sync(int id, int n) { asm volatile("bar.sync %0, %1;" ::"r"(id), "r"(n) : "memory"); }
__device__ __forceinline__ void bar_arrive(int id, int n) { asm volatile("bar.arrive %0, %1;" ::"r"(id), "r"(n) : "memory"); }
__device__ __forceinline__ void fence_async_smem() { asm volatile("fence.proxy.async.shared::cta;" ::: "memory"); }
__device__ __forceinline__ void fence_async_global() { asm volatile("fence.proxy.async.global;" ::: "memory"); }
__device__ __forceinline__ void fence_gpu() { asm volatile("fence.release.gpu;" ::: "memory"); }
__device__ __forceinline__ void expect_e(uint32_t bar, uint32_t bytes) {
    asm volatile("{\n.reg .pred p;\nelect.sync _|p, 0xffffffff;\n@p mbarrier.arrive.expect_tx.shared::cta.b64 _, [%0], %1;\n}" ::"r"(bar), "r"(bytes) : "memory");
}
__device__ __forceinline__ void tma3_e(uint32_t dst, const CUtensorMap* m, int c0, int c1, int c2, uint32_t bar) {
    asm volatile("{\n.reg .pred p;\nelect.sync _|p, 0xffffffff;\n@p cp.async.bulk.tensor.3d.shared::cluster.global.mbarrier::complete_tx::bytes [%0], [%1, {%3, %4, %5}], [%2];\n}"
                 ::"r"(dst), "l"(m), "r"(bar), "r"(c0), "r"(c1), "r"(c2) : "memory");
}
__device__ __forceinline__ void bulk_e(uint32_t dst, const void* src, uint32_t bytes, uint32_t bar) {
    asm volatile("{\n.reg .pred p;\nelect.sync _|p, 0xffffffff;\n@p cp.async.bulk.shared::cluster.global.mbarrier::complete_tx::bytes [%0], [%1], %2, [%3];\n}"
                 ::"r"(dst), "l"(src), "r"(bytes), "r"(bar) : "memory");
}
__device__ __forceinline__ void init_e(uint32_t bar, int cnt) {
    asm volatile("{\n.reg .pred p;\nelect.sync _|p, 0xffffffff;\n@p mbarrier.init.shared::cta.b64 [%0], %1;\n}" ::"r"(bar), "r"(cnt) : "memory");
}
__device__ __forceinline__ void l2_prefetch_e(const void* src, uint32_t bytes) {
    asm volatile("{\n.reg .pred p;\nelect.sync _|p, 0xffffffff;\n@p cp.async.bulk.prefetch.L2.global [%0], %1;\n}" ::"l"(src), "r"(bytes) : "memory");
}
__device__ __forceinline__ uint32_t ld_relaxed(const uint32_t* p) { uint32_t v; asm volatile("ld.relaxed.gpu.global.u32 %0, [%1];" : "=r"(v) : "l"(p) : "memory"); return v; }
__device__ __forceinline__ void st_relaxed(uint32_t* p, uint32_t v) { asm volatile("st.relaxed.gpu.global.u32 [%0], %1;" ::"l"(p), "r"(v) : "memory"); }
__device__ __forceinline__ uint4 ld_relaxed4(const uint4* p) { uint4 v; asm volatile("ld.relaxed.gpu.global.v4.u32 {%0,%1,%2,%3}, [%4];" : "=r"(v.x), "=r"(v.y), "=r"(v.z), "=r"(v.w) : "l"(p) : "memory"); return v; }
__device__ __forceinline__ uint4 lds4(uint32_t a) { uint4 v; asm volatile("ld.shared.v4.u32 {%0,%1,%2,%3}, [%4];" : "=r"(v.x), "=r"(v.y), "=r"(v.z), "=r"(v.w) : "r"(a) : "memory"); return v; }
__device__ __forceinline__ float2 lds2f(uint32_t a) { float2 v; asm volatile("ld.shared.v2.f32 {%0,%1}, [%2];" : "=f"(v.x), "=f"(v.y) : "r"(a) : "memory"); return v; }
__device__ __forceinline__ uint32_t lds1(uint32_t a) { uint32_t v; asm volatile("ld.shared.u32 %0, [%1];" : "=r"(v) : "r"(a) : "memory"); return v; }
__device__ __forceinline__ void sts4(uint32_t a, uint4 v) { asm volatile("st.shared.v4.u32 [%0], {%1,%2,%3,%4};" ::"r"(a), "r"(v.x), "r"(v.y), "r"(v.z), "r"(v.w) : "memory"); }
__device__ __forceinline__ void sts1(uint32_t a, uint32_t v) { asm volatile("st.shared.u32 [%0], %1;" ::"r"(a), "r"(v) : "memory"); }
__device__ __forceinline__ void stsm4(uint32_t a, uint32_t r0, uint32_t r1, uint32_t r2, uint32_t r3) {
    asm volatile("stmatrix.sync.aligned.m8n8.x4.shared.b16 [%0], {%1,%2,%3,%4};" ::"r"(a), "r"(r0), "r"(r1), "r"(r2), "r"(r3));
}
__device__ __forceinline__ uint32_t pack2(float lo, float hi) { uint32_t r; asm("cvt.rn.bf16x2.f32 %0, %1, %2;" : "=r"(r) : "f"(hi), "f"(lo)); return r; }
__device__ __forceinline__ uint32_t pack2_relu(float lo, float hi) { uint32_t r; asm("cvt.rn.relu.bf16x2.f32 %0, %1, %2;" : "=r"(r) : "f"(hi), "f"(lo)); return r; }
__device__ __forceinline__ uint32_t hfma2(uint32_t a, uint32_t b, uint32_t c) { uint32_t r; asm("fma.rn.bf16x2 %0, %1, %2, %3;" : "=r"(r) : "r"(a), "r"(b), "r"(c)); return r; }
__device__ __forceinline__ uint32_t hmul2(uint32_t a, uint32_t b) { uint32_t r; asm("mul.rn.bf16x2 %0, %1, %2;" : "=r"(r) : "r"(a), "r"(b)); return r; }
__device__ __forceinline__ float bf_lo(uint32_t v) { return __uint_as_float(v << 16); }
__device__ __forceinline__ float bf_hi(uint32_t v) { return __uint_as_float(v & 0xFFFF0000u); }
__device__ __forceinline__ float bf_round(float v) { return bf_lo(pack2(v, 0.f)); }
__device__ __forceinline__ float ex2(float x) { float r; asm("ex2.approx.ftz.f32 %0, %1;" : "=f"(r) : "f"(x)); return r; }
__device__ __forceinline__ void mma16816(float* d, uint32_t a0, uint32_t a1, uint32_t a2, uint32_t a3, uint32_t b0, uint32_t b1) {
    asm("mma.sync.aligned.m16n8k16.row.col.f32.bf16.bf16.f32 {%0,%1,%2,%3}, {%4,%5,%6,%7}, {%8,%9}, {%0,%1,%2,%3};"
        : "+f"(d[0]), "+f"(d[1]), "+f"(d[2]), "+f"(d[3]) : "r"(a0), "r"(a1), "r"(a2), "r"(a3), "r"(b0), "r"(b1));
}
__device__ __forceinline__ void mma1688(float* d, uint32_t a0, uint32_t a1, uint32_t b0) {
    asm("mma.sync.aligned.m16n8k8.row.col.f32.bf16.bf16.f32 {%0,%1,%2,%3}, {%4,%5}, {%6}, {%0,%1,%2,%3};"
        : "+f"(d[0]), "+f"(d[1]), "+f"(d[2]), "+f"(d[3]) : "r"(a0), "r"(a1), "r"(b0));
}
__device__ __forceinline__ void ldsm4(uint32_t a, uint32_t* r) {
    asm volatile("ldmatrix.sync.aligned.m8n8.x4.shared.b16 {%0,%1,%2,%3}, [%4];" : "=r"(r[0]), "=r"(r[1]), "=r"(r[2]), "=r"(r[3]) : "r"(a));
}
__device__ __forceinline__ void ldsm4t(uint32_t a, uint32_t* r) {
    asm volatile("ldmatrix.sync.aligned.m8n8.x4.trans.shared.b16 {%0,%1,%2,%3}, [%4];" : "=r"(r[0]), "=r"(r[1]), "=r"(r[2]), "=r"(r[3]) : "r"(a));
}
__device__ __forceinline__ uint32_t nz(uint32_t v) { uint32_t r; asm("max.u32 %0, %1, 1;" : "=r"(r) : "r"(v)); return r; }
__device__ __forceinline__ float rcp(float x) { float r; asm("rcp.approx.ftz.f32 %0, %1;" : "=f"(r) : "f"(x)); return r; }
__device__ __forceinline__ uint2 ld_relaxed2(const void* p) { uint2 v; asm volatile("ld.relaxed.gpu.global.v2.u32 {%0,%1}, [%2];" : "=r"(v.x), "=r"(v.y) : "l"(p) : "memory"); return v; }
__host__ __device__ constexpr uint64_t dconst(uint32_t lbo, uint32_t sbo, uint32_t swz) {
    return ((uint64_t)(lbo >> 4) << 16) | ((uint64_t)(sbo >> 4) << 32) | ((uint64_t)swz << 62);
}
__device__ __forceinline__ uint32_t mkdesc(uint32_t addr, uint64_t c) { return (uint32_t)c | ((addr & 0x3FFFF) >> 4); }
#define WG_FENCE() asm volatile("wgmma.fence.sync.aligned;" ::: "memory")
#define WG_COMMIT() asm volatile("wgmma.commit_group.sync.aligned;" ::: "memory")
#define WG_WAIT(n) asm volatile("wgmma.wait_group.sync.aligned %0;" ::"n"(n) : "memory")
template <int N> __device__ __forceinline__ void reg_fence(float* d) {
#pragma unroll
    for (int i = 0; i < N; i++) asm volatile("" : "+f"(d[i])::"memory");
}
template <int N> __device__ __forceinline__ void reg_def(float* d) {
#pragma unroll
    for (int i = 0; i < N; i++) asm volatile("" : "=f"(d[i]));
}
template <int N> __device__ __forceinline__ void reg_def(uint32_t* d) {
#pragma unroll
    for (int i = 0; i < N; i++) asm volatile("" : "=r"(d[i]));
}
__device__ __forceinline__ void wait_flags(const uint32_t* p, uint32_t target, uint32_t mask) {
    int n = 0;
    while (~__ballot_sync(~0u, ld_relaxed(p) == target) & mask) { if (++n > SPIN_LIMIT) __trap(); }
    asm volatile("fence.acquire.gpu;" ::: "memory");
}
__device__ __forceinline__ float silu_bf(uint32_t cbits) {
    const float c = __uint_as_float(cbits << 16);
    return bf_round(__fdividef(c, 1.f + fminf(ex2(-1.4426950408889634f * c), 1e30f)));
}
__device__ __forceinline__ void gemv_part(uint32_t wmbuf, int wp, int lane) {
    const uint32_t wa = wmbuf + wp * 512 + (8 * (lane >> 4) + (lane & 7)) * 32 + ((lane >> 3) & 1) * 16;
    float d[4] = {};
#pragma unroll
    for (int i = 0; i < 4; i++) {
        uint32_t A[4];
        const float2 v = lds2f(wmbuf + 28672 + (wp + 8 * i) * 32 + (lane & 3) * 8);
        ldsm4t(wa + (i < 3 || wp < 4 ? i : 0) * 4096, A);
        mma16816(d, A[0], A[1], A[2], A[3], __float_as_uint(v.x), __float_as_uint(v.y));
    }
    if ((lane & 3) == 0) {
        sts1(wmbuf + 29696 + (wp * 16 + (lane >> 2)) * 4, __float_as_uint(d[0]));
        sts1(wmbuf + 29696 + (wp * 16 + 8 + (lane >> 2)) * 4, __float_as_uint(d[2]));
    }
}
__device__ __forceinline__ uint32_t mod_word(float v, int col, uint32_t target) {
    v = bf_round(v);
    if ((col >= DM && col < 2 * DM) || (col >= 4 * DM && col < 5 * DM)) v += 1.f;
    return (pack2(v, 0.f) << 16) | (target & 0xFFFFu);
}
__device__ __forceinline__ const uint4* mod_src(int i, int r, int j, bool p2) {
    i = min(i, p2 ? 251 : 223);
    return (const uint4*)g_mod + (r & 7) * (6 * DM / 4) + (i < 224 ? (p2 ? 336 : 0) + i : (i < 238 ? 14 * j + i : 14 * j + i + 322));
}
__device__ __forceinline__ void mod_store(uint32_t sb, uint4 v, const uint4* src, int i) {
    const uint32_t tag = lds1(sb + M_EPOCH) + 1;
    while (__any_sync(~0u, (((v.x ^ tag) | (v.y ^ tag) | (v.z ^ tag) | (v.w ^ tag)) & 0xFFFFu) != 0u)) v = ld_relaxed4(src);
    if (i < 224) {
        const int isc = i >= 112, c4 = i - 112 * isc;
        const uint32_t a = sb + M_ST + (c4 >> 2) * 64 + (c4 & 1) * 32 + (c4 & 2) * 4 + (isc ? 0 : 4);
        sts1(a, __byte_perm(v.x, v.y, 0x7632));
        sts1(a + 16, __byte_perm(v.z, v.w, 0x7632));
    } else if (i < 252) {
        sts4(sb + M_G + (i - 224) * 16, make_uint4(v.x & 0xFFFF0000u, v.y & 0xFFFF0000u, v.z & 0xFFFF0000u, v.w & 0xFFFF0000u));
    }
}
__device__ __forceinline__ int pass_f(int fs, int ps) { return 224 * fs + ((fs & 1) ? (ps == 0 ? 96 : ps == 1 ? 32 : 0) : (ps == 0 ? 0 : ps == 1 ? 128 : 192)); }
__device__ __forceinline__ constexpr uint32_t slot_off(int l) { return l * 16384; }
__device__ __forceinline__ constexpr int g1_slot(int s) { return s % 7; }
__device__ __noinline__ void x1_fix(const uint32_t* g, uint32_t sa, int s) {
#pragma unroll 1
    for (int k = 4 * s; k < 4 * s + 4;) {
        const uint4 v = ld_relaxed4((const uint4*)(g + k * 256));
        sts4(sa + k * 1024, v);
        k += 2 * __all_sync(~0u, min(min(v.x, v.y), min(v.z, v.w)) != 0u);
    }
    __syncwarp();
}
struct LnRow { uint32_t nm, hi, lo; };
__device__ __forceinline__ LnRow ln_coeffs(float mean, float msq) {
    const float var = bf_round(fmaxf(msq - mean * mean, 0.f));
    float sd;
    asm("sqrt.approx.f32 %0, %1;" : "=f"(sd) : "f"(bf_round(var + 1e-5f)));
    const float inv = rcp(bf_round(sd)), hi = bf_round(inv);
    LnRow c;
    c.nm = pack2(-bf_round(mean) * hi, -bf_round(mean) * hi);
    c.hi = pack2(hi, hi);
    c.lo = pack2(inv - hi, inv - hi);
    return c;
}
__device__ __forceinline__ uint32_t ln_norm(uint32_t x, const LnRow& c) {
    return hfma2(x, c.hi, c.nm);
}
__device__ __forceinline__ uint32_t ln_mod(uint32_t y, uint32_t sc, uint32_t sh) {
    return hfma2(y, sc, sh);
}

#define LOADW bulk_e(dst, g_wd + (size_t)((f >> 5) * 4 + nq) * 1792, 7168, bar);
template <int sec> __device__ __forceinline__ void ring_loader(const Params& p, uint32_t sb_, int r_, int j_, int lane) {
    const uint32_t sb = opaque(sb_);
    const int r = opaque(r_), j = opaque(j_), nq = j >> 1, fs = 4 * (j & 1) + nq;
    const int fa = pass_f(fs, 0), fb = pass_f(fs, 1), fc = pass_f(fs, 2);
    const uint32_t* h2src = (const uint32_t*)__shfl_sync(~0u, (unsigned long long)(p.actb + (size_t)r * RB_WORDS + RB_H2), 0);
    const CUtensorMap* gmap = (const CUtensorMap*)__shfl_sync(~0u, (unsigned long long)(&p.ga + sec), 0);
#define BAR(i) (sb + M_BAR + 8 * (i))
#define kh (j & 1)
            int sl = 0;
#pragma unroll 1
            for (int s = 0; s < 28; s++) {
                if (s == 7) { wait_flags(g_flag + (8 * r + j) * 128 + 96 + lane, lds1(sb + M_EPOCH) + 1, 0xFFFFu); fence_async_global(); }
                const int ps = s < 14 ? 0 : s < 21 ? 1 : 2;
                const uint32_t half = ps < 2 ? 8192 : 4096;
                const int sp = sl;
                if (s >= 1 && s < 6) mbar_wait(BAR(B_FULL + s - 1), 0);
                mbar_wait(BAR(B_EMPTY + sp), (s >= 7 && s < 14) || s >= 21);
                expect_e(BAR(B_FULL + sp), half);
                tma3_e(sb + slot_off(sp) + sec * half, gmap + 2 * ps, 0, ps ? 64 * sl : 32 * s, ps == 0 ? fa >> 6 : ps == 1 ? fb >> 6 : fc >> 5, BAR(B_FULL + sp));
                sl = sl == 6 ? 0 : sl + 1;
            }
            if (!sec) PROFH(3);
            if (sec) asm volatile("prefetch.tensormap [%0];" ::"l"(&p.om) : "memory");
#pragma unroll 1
            for (int e = 0; e < 4; e++) {
                const uint32_t dst = sb + slot_off(e) + sec * 8192, bar = BAR(B_FULL + e);
                const int f = (e < 2 ? fa + 64 * e : e == 2 ? fb : fc) + 32 * sec;
                mbar_wait(BAR(B_EMPTY + e), 0);
                expect_e(bar, e == 3 && sec ? 0 : 7168);
                if (!(e == 3 && sec)) { LOADW }
            }
            sl = 4;
            int e = 4;
#pragma unroll 1
            for (int grp = 0; grp < 9; grp++) {
                const int ps = grp >= 6 ? 2 : grp >= 3 ? 1 : 0;
                int sidx = grp - 3 * ps;
                if (sec && sidx == 0) { mbar_wait(BAR(B_HRDY + ps), 0); fence_async_global(); }
                sidx += sidx >= nq;
                int f = pass_f(4 * kh + sidx, ps);
#pragma unroll 1
                for (int k = 4 >> ps; k > 0; k--, e++, f += 32) {
                    const uint32_t dst = sb + slot_off(sl), bar = BAR(B_FULL + sl);
                    mbar_wait(BAR(B_EMPTY + sl), e >= 12 && e < 24);
                    if (e >= WIN) mbar_wait(BAR(B_FULL + (sl >= WIN ? sl - WIN : sl + 12 - WIN)), e - WIN >= 12);
                    expect_e(bar, sec ? 8192 : 7168);
                    if (!sec) { LOADW }
                    else bulk_e(dst + 8192, h2src + f * 64, 8192, bar);
                    sl = sl == 11 ? 0 : sl + 1;
                }
            }
            if (!sec) PROFH(4);
}

#define PROF_PARAMS
#define PROF_ARGS
__device__ __noinline__ void helper_late(const Params& p, int r_, int j_, int warp_ PROF_PARAMS) {
    extern __shared__ __align__(1024) unsigned char smem[];
    const uint32_t sb = (uint32_t)__cvta_generic_to_shared(smem);
    const int r = opaque(r_), j = opaque(j_), warp = opaque(warp_), nq = j >> 1, b = 8 * r + j;
    uint32_t* const act = (uint32_t*)__shfl_sync(~0u, (unsigned long long)(p.actb + (size_t)r * RB_WORDS), 0);
    {
        const int lane = fresh_tid() & 31;
        const uint32_t target = lds1(sb + M_EPOCH) + 1;
        if (warp == 8) { expect_e(BAR(B_XCH), 7168); expect_e(BAR(B_XCH + 1), 7168); }
            if (warp == 9) {
#pragma unroll 1
                for (int kv = 0; kv < 2; kv++) {
                    mbar_wait(BAR(B_PUB + kv), 0);
                    wait_flags(g_flag + b * 128 + lane, target, (r >= 2 ? 6u : r == 1 ? 2u : 0u) << (8 * kv));
                    fence_async_global();
                    const uint32_t dst = sb + OFF_Y + (kv ? Y_VR : Y_K);
                    expect_e(BAR(B_KRFULL + kv), r >= 2 ? 28672 : r == 1 ? 14336 : 0);
                    if (r >= 2) bulk_e(dst, act - 2 * RB_WORDS + RB_KV + j * 7168 + kv * 3584, 14336, BAR(B_KRFULL + kv));
                    if (r >= 1) bulk_e(dst + 14336, act - RB_WORDS + RB_KV + j * 7168 + kv * 3584, 14336, BAR(B_KRFULL + kv));
                    if (kv == 0) { PROFH(8); }
                }
            } else if (warp == 8) {
                uint4 v[8];
                mbar_wait(BAR(B_WOFULL), 0);
#pragma unroll
                for (int k = 0; k < 8; k++) v[k] = ld_relaxed4(mod_src(lane + 32 * k, r, j, true));
#pragma unroll
                for (int k = 0; k < 8; k++) mod_store(sb, v[k], mod_src(lane + 32 * k, r, j, true), lane + 32 * k);
                warp_arrive(BAR(B_MOD1));
            } else if (warp == 11) {
                if (kh == 1 && r < 14) {
                    const uint32_t wmbuf = sb + OFF_X + HALF;
                    const int mcol = 2 * DM + 32 * (4 * r + nq);
                    mbar_wait(BAR(B_XFREE), 0);
                    tma3_e(wmbuf, &p.wm2, mcol, 0, 0, BAR(B_WMFULL));
                    tma3_e(wmbuf + 14336, &p.wm2, mcol, 224, 0, BAR(B_WMFULL));
#pragma unroll 1
                    for (int wd = lane; wd < 224; wd += 32) {
                        const uint32_t cb = __ldg((const uint32_t*)p.c + wd);
                        sts1(wmbuf + 28672 + (wd >> 3) * 32 + (wd & 3) * 8 + (wd & 4), pack2(silu_bf(cb & 0xFFFFu), silu_bf(cb >> 16)));
                    }
                    __syncwarp();
                    mbar_wait(BAR(B_WMFULL), 0);
                    const uint32_t wa = wmbuf + (8 * (lane >> 4) + (lane & 7)) * 64 + ((lane >> 3) & 1) * 16;
                    float d[2][4] = {};
#pragma unroll 4
                    for (int ks = 0; ks < 28; ks++) {
                        uint32_t A[8];
                        ldsm4t(wa + ks * 1024, A); ldsm4t(wa + ks * 1024 + 32, A + 4);
                        const float2 v = lds2f(wmbuf + 28672 + ks * 32 + (lane & 3) * 8);
                        mma16816(d[0], A[0], A[1], A[2], A[3], __float_as_uint(v.x), __float_as_uint(v.y));
                        mma16816(d[1], A[4], A[5], A[6], A[7], __float_as_uint(v.x), __float_as_uint(v.y));
                    }
                    const int q = lane & 3, col = mcol + 8 * q + (lane >> 2);
                    const uint32_t word = mod_word(q == 0 ? d[0][0] : q == 1 ? d[0][2] : q == 2 ? d[1][0] : d[1][2], col, target);
#pragma unroll
                    for (int i = 0; i < 8; i++) st_relaxed(g_mod + i * 6 * DM + col, word);
                }
                warp_arrive(BAR(B_WMFREE));
                mbar_wait(BAR(B_VRFULL), 0);
                l2_prefetch_e((const char*)p.wg + (size_t)b * 12544, 12544);
                l2_prefetch_e((const char*)p.wu + (size_t)b * 12544, 12544);
#pragma unroll 1
                for (int k = 0; k < (r < 12 ? 2 : 1); k++) {
                    const int u = 28 * kh + r + 16 * k;
                    expect_e(BAR(B_XFULL + k), 7168);
                    tma3_e(sb + OFF_Y + 102400, &p.dn, 0, 32 * u, 7 * j, BAR(B_XFULL + k));
                    tma3_e(sb + OFF_Y + 102400 + 3584, &p.dn, 0, 32 * u, 7 * (j ^ 1), BAR(B_XFULL + k));
                    mbar_wait(BAR(B_XFULL + k), 1);
                    asm volatile("{\n.reg .pred p;\nelect.sync _|p, 0xffffffff;\n@p cp.async.bulk.global.shared::cta.bulk_group [%0], [%1], 7168;\n"
                                 "cp.async.bulk.commit_group;\ncp.async.bulk.wait_group 0;\n}" ::"l"(g_wd + (size_t)(u * 4 + nq) * 1792), "r"(sb + OFF_Y + 102400) : "memory");
                    __syncwarp();
                }
                warp_arrive(BAR(B_FULLK));
                fence_gpu();
                if (lane < 16) st_relaxed(g_flag + (8 * lane + j) * 128 + 96 + r, target);
            }
        if (warp == 8 || warp == 11) {
            const int sec = warp == 11;
            if (sec) ring_loader<1>(p, sb, r, j, lane); else ring_loader<0>(p, sb, r, j, lane);
            mbar_wait(BAR(B_DONE), 0);
        } else if (warp == 9) {
#pragma unroll
            for (int ev = 0; ev < 4; ev++) { expect_e(BAR(B_GFULL + ev), ev < 2 ? HALF / 2 : 16384); expect_e(BAR(B_XFULL + 2 + ev), ev < 2 ? HALF / 2 : HALF - 16384); }
            mbar_wait(BAR(B_PUB + 2), 0);
            expect_e(BAR(B_FULLV), 4096); expect_e(BAR(B_FULLQ), 4096);
            const uint32_t* fp = g_flag + b * 128 + 32 + lane;
            const int par = (target - 1) & 1;
#pragma unroll 1
            for (int n = 0, ev = 0; ev < 4; n++) {
                if (ev == 1) mbar_wait(BAR(B_PUB + 3), 0);
                uint32_t ok = __ballot_sync(~0u, ld_relaxed(fp) == target) >> (8 * ev);
                while ((ok & 0xFFu) == 0xFFu) {
                    if (ev == 1) mbar_wait(BAR(B_FULLK), 1);
                    asm volatile("fence.acquire.gpu;" ::: "memory");
                    fence_async_global();
                    const int tile = (ev & 1) + (ev >> 1) * par * 2;
                    const uint32_t dst = sb + (ev == 0 ? OFF_X : OFF_Y + (ev & 1) * HALF), first = ev < 2 ? HALF / 2 : 16384;
                    const char* src = (const char*)(act + RB_O + ((ev >> 1) * 2 + tile) * 14336);
                    if (ev >= 2) bulk_e(sb + OFF_X + X_STAT + (ev & 1) * 49152, act + RB_ST + tile * 1024, 4096, BAR(B_FULLV + (ev & 1)));
                    bulk_e(dst, src, first, BAR(B_GFULL + ev));
                    bulk_e(dst + first, src + first, HALF - first, BAR(B_XFULL + 2 + ev));
                    if (ev) PROFH(4 + ev);
                    ev++; ok >>= 8;
                }
                if (n > SPIN_LIMIT) __trap();
            }
            mbar_wait(BAR(B_XFULL + 5), 1);
#pragma unroll 1
            for (int hf = 0; hf < 2; hf++) {
                const int tile = (par ^ 1) * 2 + hf;
                uint4* xz = (uint4*)(act + RB_X1 + tile * 14336 + j * 1792) + lane;
#pragma unroll
                for (int i = 0; i < 14; i++) xz[i * 32] = make_uint4(0, 0, 0, 0);
                ((uint4*)(act + RB_ST + (tile * 8 + j) * 128))[lane] = make_uint4(0, 0, 0, 0);
            }
#pragma unroll 1
            for (int ps = 0; ps < 3; ps++) {
                mbar_wait(BAR(B_PUB + 6 + ps), 0);
                if (ps == 1) {
                    fence_gpu();
                    if (lane < 8) st_relaxed(g_flag + (8 * r + lane) * 128 + 72 + j, target);
                }
                wait_flags(g_flag + b * 128 + 64 + lane, target, (0x55u << kh) << (8 * ps));
                warp_arrive(BAR(B_HRDY + ps));
                PROFH(9 + ps);
            }
        } else {
#pragma unroll 1
            for (int k = 0; k < 9; k++) {
                if (k == 7) continue;
                uint32_t* fp = k < 2 ? g_flag + (b + 8 * lane) * 128 + k * 8 + lane : g_flag + (8 * r + lane) * 128 + 16 + k * 8 + j;
                mbar_wait(BAR(B_PUB + k), 0);
                if (k != 4 && k != 5) fence_gpu();
                if (k < 2 ? (lane == 1 || lane == 2) : lane < 8) st_relaxed(fp, target);
                if (k >= 3 && k <= 5) PROFH(k - 3);
            }
        }
    }
}

__global__ void __cluster_dims__(2, 1, 1) __launch_bounds__(384, 1) fused_block_kernel(const __grid_constant__ Params p) {
    extern __shared__ __align__(1024) unsigned char smem[];
    const uint32_t sb = (uint32_t)__cvta_generic_to_shared(smem);
    const int tid = threadIdx.x, lane = tid & 31, warp = __shfl_sync(~0u, tid >> 5, 0);
    const int m = blockIdx.x >> 1;
    int r, nq;
    if (m < 4) { r = 15; nq = m; }
    else if (m < 36) { r = (m - 4) & 7; nq = (m - 4) >> 3; }
    else { nq = (m - 36) / 7; r = m - 28 - 7 * nq; }
    const int j = opaque(2 * nq + (blockIdx.x & 1)), b = 8 * r + j, fs = 4 * kh + nq;
#define act (p.actb + (size_t)r * RB_WORDS)
    if (lane == 0 && warp < 9 && warp != 6 && warp != 7) {
        const int i0 = warp == 8 ? 0 : 8 + 8 * warp, cnt = warp == 0 || warp == 8 ? 1 : warp < 3 ? 2 : 8;
#pragma unroll
        for (int k = 0; k < 8; k++) if (i0 + k != B_WMFULL) mbar_init(BAR(i0 + k), cnt);
        if (warp == 8) mbar_init(BAR(B_WMFULL), 1);
        asm volatile("fence.mbarrier_init.release.cluster;" ::: "memory");
        fence_async_smem();
    }

    if (warp >= 8) {
        const int lane = fresh_tid() & 31;
        const bool early = kh == 0, gemv = r < 14;
        const int mcol = early ? 16 * (4 * r + nq) : 2 * DM + 32 * (4 * r + nq);
        const uint32_t wmbuf = sb + OFF_Y + HALF;
        if (warp == 8) {
            __syncwarp();
            expect_e(BAR(B_WMFULL), gemv ? 28672 >> early : 0);
            if (early && gemv) { tma3_e(wmbuf, &p.wm, mcol, 0, 0, BAR(B_WMFULL)); tma3_e(wmbuf + 7168, &p.wm, mcol, 224, 0, BAR(B_WMFULL)); }
#pragma unroll
            for (int kb = 0; kb < 7; kb++) {
                expect_e(BAR(B_XFULL + kb), 16384);
                tma3_e(sb + OFF_X + kb * 16384, &p.xm, 64 * kb, 128 * r, 0, BAR(B_XFULL + kb));
            }
        }
        asm volatile("setmaxnreg.dec.sync.aligned.u32 56;");
        if (warp == 9) {
#pragma unroll
            for (int i = 56; i < 64; i++) init_e(BAR(i), 1);
            fence_async_smem();
        }
        bar_arrive(0, 384);
        asm volatile("barrier.cluster.arrive.relaxed.aligned;" ::: "memory");
        if (warp == 8) {
            mbar_wait(BAR(B_XFULL), 0);
            l2_prefetch_e((const char*)p.wqkv + (size_t)b * 9408, 9408);
#pragma unroll 1
            for (int mt = 0; mt < 4; mt++) {
                if (mt == 1) bar_sync(9, 384);
                if (mt == 3) mbar_wait(BAR(B_WMFREE), 0);
                if (mt == 1 && early) mbar_wait(BAR(B_WMFREE), 0);
                if (mt) mbar_wait(BAR(mt == 1 ? B_FULLK : mt == 2 ? B_MOD1 : B_VRFULL), 0);
                const uint32_t bar = BAR(mt == 3 ? B_WOFULL : B_FULLK + mt), dst = sb + (mt < 2 ? OFF_Y : OFF_X) + (mt & 1) * HALF;
                const int c0 = (mt < 2 ? DM + DM * mt : 0) + 56 * j - 8 * kh;
                expect_e(bar, HALF);
                tma3_e(dst, mt == 3 ? &p.wo : &p.qkv, c0, 0, 0, bar);
                tma3_e(dst + HALF / 2, mt == 3 ? &p.wo : &p.qkv, c0, 224, 0, bar);
            }
        } else {
            if (warp == 10 && lane < 13) asm volatile("prefetch.tensormap [%0];" ::"l"(&p.wm + lane) : "memory");
            bar_sync(9, 384);
            if (warp == 11 && early) {
                const uint32_t target = lds1(sb + M_EPOCH) + 1;
                mbar_wait(BAR(B_GEMV), 0);
                float sum = 0.f;
#pragma unroll
                for (int i = 0; i < 8; i++) sum += *(const float*)(smem + OFF_Y + HALF + 29696 + (i * 16 + (lane & 15)) * 4);
                uint32_t* mg = g_mod + mcol + (lane & 15) + (lane >> 4) * 4 * 6 * DM;
                const uint32_t word = mod_word(sum, mcol, target);
                if (gemv) { st_relaxed(mg, word); st_relaxed(mg + 6 * DM, word); st_relaxed(mg + 12 * DM, word); st_relaxed(mg + 18 * DM, word); }
            }
        }
    }
    if (warp < 8) {
        const int w = (warp >> 2) ^ 1, wi = warp & 3;
#define COORDS const int t = fresh_tid() & 127, lane = t & 31, q = lane & 3, lr = lane >> 2, ra = 64 * w + 16 * wi + lr; \
        const uint32_t lx = (lane >> 4) ^ (lane & 7), mrow = (64 * w + 16 * wi + ((lane >> 3) & 1) * 8 + (lane & 7)) * 128; \
        (void)q; (void)lr; (void)ra; (void)lx; (void)mrow;
#define WAIT(i, par) mbar_wait_c(BAR(i), par)
        constexpr uint64_t DB128 = dconst(4096, 1024, 1);
        {
            const int wd = fresh_tid();
            const uint32_t cb = wd < 224 ? __ldg((const uint32_t*)p.c + wd) : 0u;
            if (wd == 255) sts1(sb + M_EPOCH, atomicAdd(&g_ticket, 1u) / NCTA);
            sts1(sb + OFF_Y + HALF + 28672 + (wd >> 3) * 32 + (wd & 3) * 8 + (wd & 4), pack2(silu_bf(cb & 0xFFFFu), silu_bf(cb >> 16)));
        }
        bar_arrive(9, 384);
        bar_sync(0, 384);
        asm volatile("barrier.cluster.arrive.relaxed.aligned;" ::: "memory");
        asm volatile("setmaxnreg.inc.sync.aligned.u32 224;");
        PROFC(0);
        uint32_t xr[16];
        {
            COORDS
            uint32_t h[112];
            LnRow ca, cb;
            const int mi = min(128 * w + t, 223);
            const uint4* msrc = mod_src(mi, r, j, false);
            uint4 mv;
            {
                float ds[4] = {}, da[2][4] = {}, db[2][4] = {};
                const uint32_t ONE2 = 0x3F803F80u;
#pragma unroll
                for (int kb = 0; kb < 7; kb++) {
                    if (kb == 0 && kh == 0) { WAIT(B_WMFULL, 0); gemv_part(sb + OFF_Y + HALF, warp, lane); warp_arrive(BAR(B_GEMV)); }
                    WAIT(B_XFULL + kb, 0);
#pragma unroll
                    for (int k4 = 0; k4 < 4; k4++) ldsm4(sb + OFF_X + mrow + kb * 16384 + (((2 * k4) ^ lx) << 4), h + 16 * kb + 4 * k4);
#pragma unroll
                    for (int k4 = 0; k4 < 4; k4++) {
                        const uint32_t* f = h + 16 * kb + 4 * k4;
                        mma16816(ds, f[0], f[1], f[2], f[3], ONE2, ONE2);
                        mma1688(da[0], f[0], f[1], f[0]); mma1688(db[0], f[0], f[1], f[1]);
                        mma1688(da[1], f[2], f[3], f[2]); mma1688(db[1], f[2], f[3], f[3]);
                    }
                }
#pragma unroll
                for (int i = 0; i < 4; i++) {
                    const int ch = 7 * j + 2 * i + (lane >> 4);
                    ldsm4(sb + OFF_X + mrow + (ch >> 3) * 16384 + (((ch ^ lane) & 7) << 4), xr + 4 * i);
                }
                mv = ld_relaxed4(msrc);
                warp_arrive(BAR(B_XFREE));
                float qa = (lr & 1) ? da[0][1] + da[1][1] : da[0][0] + da[1][0];
                float qb = (lr & 1) ? db[0][3] + db[1][3] : db[0][2] + db[1][2];
                const int src = (lane & ~3) | (lr >> 1);
                qa = __shfl_sync(~0u, qa, src);
                qb = __shfl_sync(~0u, qb, src);
                ca = ln_coeffs(ds[0] * (1.f / DM), qa * (1.f / DM));
                cb = ln_coeffs(ds[2] * (1.f / DM), qb * (1.f / DM));
#pragma unroll
                for (int i = 0; i < 4 * NPRE; i += 2) { h[i] = ln_norm(h[i], ca); h[i + 1] = ln_norm(h[i + 1], cb); }
            }
            PROFC(1);
            {
                float ak[28], av[28], aq[28];
                uint32_t kp[14], vp[14];
                const uint64_t bq0 = (DB128 & ~0xFFFFFFFFull) | (mkdesc(sb + OFF_X, DB128) + kh), bk0 = bq0 + (OFF_Y >> 4), bv0 = bk0 + (HALF >> 4);
                uint32_t* kvg = act + RB_KV + j * 7168 + (8 * w + 2 * wi) * 224 + lane;
                mod_store(sb, mv, msrc, mi);
                bar_sync(3, 256);
                if (warp == 0) warp_arrive(BAR(B_MOD1));
                WAIT(B_FULLK, 0);
                PROFC(2);
                reg_def<28>(ak);
#pragma unroll
                for (int g4 = 0; g4 < 4; g4++) {
#pragma unroll
                    for (int ks = 7 * g4; ks < 7 * g4 + 7; ks++) {
                        const uint4 st = *(const uint4*)(smem + M_ST + ks * 64 + q * 16);
                        if (ks >= NPRE) {
                            h[4 * ks] = ln_norm(h[4 * ks], ca); h[4 * ks + 1] = ln_norm(h[4 * ks + 1], cb);
                            h[4 * ks + 2] = ln_norm(h[4 * ks + 2], ca); h[4 * ks + 3] = ln_norm(h[4 * ks + 3], cb);
                        }
                        h[4 * ks] = ln_mod(h[4 * ks], st.x, st.y); h[4 * ks + 1] = ln_mod(h[4 * ks + 1], st.x, st.y);
                        h[4 * ks + 2] = ln_mod(h[4 * ks + 2], st.z, st.w); h[4 * ks + 3] = ln_mod(h[4 * ks + 3], st.z, st.w);
                    }
                    WG_FENCE();
#pragma unroll
                    for (int ks = 7 * g4; ks < 7 * g4 + 7; ks++) wgmma_rl_56(ak, h[4 * ks], h[4 * ks + 1], h[4 * ks + 2], h[4 * ks + 3], bk0 + ks * 128, ks != 0);
                }
                WG_COMMIT();
                PROFC(3);
                reg_def<28>(av);
                WG_WAIT(0);
                reg_fence<28>(ak);
#pragma unroll
                for (int g = 0; g < 7; g++) {
                    kp[2 * g] = pack2(ak[4 * g], ak[4 * g + 1]); kp[2 * g + 1] = pack2(ak[4 * g + 2], ak[4 * g + 3]);
                    kvg[g * 32] = kp[2 * g]; kvg[224 + g * 32] = kp[2 * g + 1];
                }
                warp_arrive(BAR(B_PUB));
                PROFC(4);
                WAIT(B_FULLV, 0);
                WG_FENCE();
#pragma unroll
                for (int ks = 0; ks < 28; ks++) wgmma_rl_56(av, h[4 * ks], h[4 * ks + 1], h[4 * ks + 2], h[4 * ks + 3], bv0 + ks * 128, ks != 0);
                WG_COMMIT();
                reg_def<28>(aq);
                WAIT(B_FULLQ, 0);
                WG_FENCE();
#pragma unroll
                for (int ks = 0; ks < VPRE; ks++) wgmma_rl_56(aq, h[4 * ks], h[4 * ks + 1], h[4 * ks + 2], h[4 * ks + 3], bq0 + ks * 128, ks != 0);
                WG_COMMIT();
                WG_WAIT(1);
                reg_fence<28>(av);
#pragma unroll
                for (int g = 0; g < 7; g++) {
                    vp[2 * g] = pack2(av[4 * g], av[4 * g + 1]); vp[2 * g + 1] = pack2(av[4 * g + 2], av[4 * g + 3]);
                    kvg[3584 + g * 32] = vp[2 * g]; kvg[3584 + 224 + g * 32] = vp[2 * g + 1];
                }
                warp_arrive(BAR(B_PUB + 1));
                PROFC(5);
                WG_FENCE();
#pragma unroll
                for (int ks = VPRE; ks < 28; ks++) wgmma_rl_56(aq, h[4 * ks], h[4 * ks + 1], h[4 * ks + 2], h[4 * ks + 3], bq0 + ks * 128, ks != 0);
                WG_COMMIT();
                WAIT(B_PUB + 1, 0);
                const uint32_t rg = 8 * w + 2 * wi + ((lane >> 3) & 1);
                const uint32_t ko = sb + OFF_Y + Y_KOWN + rg * 896 + (lane & 7) * 16, qo = sb + OFF_Y + Y_Q + rg * 1024 + (lane >> 4) * 128 + (lane & 7) * 16;
#pragma unroll
                for (int g = 0; g < 6; g += 2) {
                    stsm4(ko + (g + (lane >> 4)) * 128, kp[2 * g], kp[2 * g + 1], kp[2 * g + 2], kp[2 * g + 3]);
                    stsm4(ko + (Y_VOWN - Y_KOWN) + (g + (lane >> 4)) * 128, vp[2 * g], vp[2 * g + 1], vp[2 * g + 2], vp[2 * g + 3]);
                }
                stsm4(ko + (lane >> 4) * (Y_VOWN - Y_KOWN) + 6 * 128, kp[12], kp[13], vp[12], vp[13]);
                WG_WAIT(0);
                reg_fence<28>(aq);
                __syncwarp();
                if (lane < 3 && w == 1) mbar_arrive(BAR(B_EMPTY + lane));
                uint32_t qp[14];
#pragma unroll
                for (int i = 0; i < 14; i++) qp[i] = pack2(aq[2 * i], aq[2 * i + 1]);
                stsm4(qo, qp[0], qp[1], qp[2], qp[3]);
                stsm4(qo + 256, qp[4], qp[5], q < 2 ? qp[6] : 0u, q < 2 ? qp[7] : 0u);
                stsm4(qo + 512, q < 2 ? 0u : qp[6], q < 2 ? 0u : qp[7], qp[8], qp[9]);
                stsm4(qo + 768, qp[10], qp[11], qp[12], qp[13]);
                fence_async_smem();
                if (w == 0) { bar_arrive(4, 256); bar_sync(1, 128); } else { bar_arrive(5, 256); bar_sync(4, 256); }
            }
        }
        PROFC(6);
        WAIT(B_KRFULL, 0);
        PROFC(7);
        {
#pragma unroll 1
            for (int hf = 0; hf < 2; hf++) {
                COORDS
                if (hf > w) bar_sync(5, 256);
                float s[160];
                const float CS = 0.18898223650461361f * 1.4426950408889634f;
                const float NEG = __int_as_float(0xFF800000);
                constexpr uint64_t DQ = dconst(128, 1024, 0), DK = dconst(128, 896, 0);
                {
                    const uint32_t qd = mkdesc(sb + OFF_Y + Y_Q + hf * 8192 + w * 512, DQ), kd = mkdesc(sb + OFF_Y + Y_K + hf * 8 * 896 + w * 384, DK);
                    reg_def<160>(s);
                    WG_FENCE();
                    wgmma_sk_160<DQ, DK>(s, qd, kd, 0);
                    wgmma_sk_160<DQ, DK>(s, qd + 16, kd + 16, 1);
                    wgmma_sk_160<DQ, DK>(s + 80, qd, kd + 20 * 56, 0);
                    wgmma_sk_160<DQ, DK>(s + 80, qd + 16, kd + 20 * 56 + 16, 1);
                    WG_COMMIT();
                    WG_WAIT(0);
                    reg_fence<160>(s);
                }
                if (r < 2) {
                    const int pmin = 4 - 2 * r - hf;
#pragma unroll
                    for (int p4 = 0; p4 < 4; p4++)
                        if (p4 < pmin) {
#pragma unroll
                            for (int i = 0; i < 32; i++) asm volatile("mov.b32 %0, 0xFF800000;" : "=f"(s[32 * p4 + i]));
                        }
                }
                const bool c0 = 2 * q > lr, c1 = 2 * q + 1 > lr;
#pragma unroll
                for (int pp = 0; pp < 4; pp++) {
                    const bool me = pp == wi;
                    float* e = s + 8 * pp;
                    if (me && !c0) { e[0] = NEG; e[6] = NEG; }
                    if (me && !c1) { e[1] = NEG; e[7] = NEG; }
                    if (me) { e[2] = NEG; e[3] = NEG; }
                    e = s + 8 * (pp + 16);
                    if (me && c0) { e[0] = NEG; e[6] = NEG; }
                    if (me && c1) { e[1] = NEG; e[7] = NEG; }
                    if (me) { e[4] = NEG; e[5] = NEG; }
                }
#pragma unroll
                for (int i = 0; i < 24; i++) s[i] = (i >> 3) < wi ? s[136 + i] : s[i];
                int i0 = 0x80000000, i1 = 0x80000000, i2 = 0x80000000, i3 = 0x80000000;
#pragma unroll
                for (int pp = 0; pp < 17; pp++) {
                    const float* e = s + 8 * pp;
                    i0 = __vimax3_s32(i0, __float_as_int(e[0]), __float_as_int(e[1])); i1 = __vimax3_s32(i1, __float_as_int(e[2]), __float_as_int(e[3]));
                    i2 = __vimax3_s32(i2, __float_as_int(e[4]), __float_as_int(e[5])); i3 = __vimax3_s32(i3, __float_as_int(e[6]), __float_as_int(e[7]));
                }
                i0 = max(i0, i2); i1 = max(i1, i3);
                i0 = max(i0, __shfl_xor_sync(~0u, i0, 1)); i1 = max(i1, __shfl_xor_sync(~0u, i1, 1));
                i0 = max(i0, __shfl_xor_sync(~0u, i0, 2)); i1 = max(i1, __shfl_xor_sync(~0u, i1, 2));
                if (__any_sync(~0u, (i0 | i1) < 0)) {
                    uint32_t u0 = ~0u, u1 = ~0u, u2 = ~0u, u3 = ~0u;
#pragma unroll
                    for (int pp = 0; pp < 17; pp++) {
                        const float* e = s + 8 * pp;
                        u0 = __vimin3_u32(u0, __float_as_uint(e[0]), __float_as_uint(e[1])); u1 = __vimin3_u32(u1, __float_as_uint(e[2]), __float_as_uint(e[3]));
                        u2 = __vimin3_u32(u2, __float_as_uint(e[4]), __float_as_uint(e[5])); u3 = __vimin3_u32(u3, __float_as_uint(e[6]), __float_as_uint(e[7]));
                    }
                    u0 = min(u0, u2); u1 = min(u1, u3);
                    u0 = min(u0, __shfl_xor_sync(~0u, u0, 1)); u1 = min(u1, __shfl_xor_sync(~0u, u1, 1));
                    u0 = min(u0, __shfl_xor_sync(~0u, u0, 2)); u1 = min(u1, __shfl_xor_sync(~0u, u1, 2));
                    if (i0 < 0) i0 = u0;
                    if (i1 < 0) i1 = u1;
                }
                const float ma = __int_as_float(i0), mb = __int_as_float(i1);
                const float na = -ma * CS, nb = -mb * CS;
                PROFC(8 + 3 * hf);
                {
                    WAIT(B_VRFULL, 0);
                    float o[16] = {}, rs[4] = {};
                    const uint32_t va = sb + OFF_Y + Y_VR + (8 * hf + ((lane >> 3) & 1)) * 896 + (3 * w + (lane >> 4)) * 128 + (lane & 7) * 16;
                    constexpr uint32_t OWN = Y_VOWN - 32 * 896;
#pragma unroll
                    for (int pp = 0; pp < 17; pp++) {
                        uint32_t B[8];
                        const uint32_t v = va + pp * 1792 + (pp < 3 ? (pp < wi ? 17 * 1792 + OWN : 0) : pp == 16 ? OWN : pp >= 12 ? hf * OWN : 0);
                        ldsm4t(v, B); ldsm4t(v + 256, B + 4);
                        float e[8];
#pragma unroll
                        for (int i = 0; i < 8; i++) e[i] = ex2(fmaf(s[8 * pp + i], CS, (i & 2) ? nb : na));
                        const uint32_t p0 = pack2(e[0], e[1]), p1 = pack2(e[2], e[3]), p2 = pack2(e[4], e[5]), p3 = pack2(e[6], e[7]);
                        mma16816(rs, p0, p1, p2, p3, 0x3F803F80u, 0x3F803F80u);
#pragma unroll
                        for (int g = 0; g < 4; g++) mma16816(o + 4 * g, p0, p1, p2, p3, B[2 * g], B[2 * g + 1]);
                    }
                    PROFC(9 + 3 * hf);
                    const float ia = rcp(rs[0]), ib = rcp(rs[2]);
                    uint32_t* og = act + RB_O + hf * 14336 + (7 * j + 3 * w) * 256 + wi * 64 + lane;
#pragma unroll
                    for (int g = 0; g < 4; g++) {
                        if ((g == 3 - 3 * w) ? ((q >> 1) == w) : true) {
                            og[g * 256] = pack2(o[4 * g] * ia, o[4 * g + 1] * ia);
                            og[g * 256 + 32] = pack2(o[4 * g + 2] * ib, o[4 * g + 3] * ib);
                        }
                    }
                    warp_arrive(BAR(B_PUB + 2 + hf));
                    PROFC(10 + 3 * hf);
                }
            }
        }
        uint32_t x1p[14];
        COORDS
        constexpr uint64_t DT = dconst(1024, 128, 0);
        const int tile = opaque((lds1(sb + M_EPOCH) & 1) * 2 + w);
        {
            float ac[28];
            const uint32_t ad = mkdesc(sb + (w ? OFF_Y + HALF : OFF_X), DT), bd = mkdesc(sb + OFF_X + HALF, DB128) + kh;
            WAIT(B_WOFULL, 0);
            WAIT(B_MOD1, 1);
            WAIT(B_GFULL + w, 0);
            PROFC(28);
            reg_def<28>(ac);
#pragma unroll 1
            for (int u = 0; u < 4; u++) {
                if (u == 2) WAIT(B_XFULL + 2 + w, 1);
                WG_FENCE();
#pragma unroll
                for (int i = 0; i < 7; i++) wgmma_ss_56<DT, DB128>(ac, ad + (7 * u + i) * 128, bd + (7 * u + i) * 128, (u | i) != 0);
            }
            WG_COMMIT();
            WG_WAIT(0);
            reg_fence<28>(ac);
            PROFC(14);
            __syncwarp();
            if (lane < 3) mbar_arrive(BAR(B_EMPTY + 4 - w + lane));
            if (lane < 3 && w == 0) mbar_arrive(BAR(B_EMPTY + lane));
            float ds[4] = {}, da[4] = {}, db[4] = {};
            uint32_t* xo = act + RB_X1 + tile * 14336 + 7 * j * 256 + wi * 64 + lane;
#pragma unroll
            for (int g = 0; g < 7; g++) {
                const float2 ga = *(const float2*)(smem + M_G + (8 * g + 2 * q) * 4);
                x1p[2 * g] = pack2(fmaf(ga.x, ac[4 * g], bf_lo(xr[2 * g])), fmaf(ga.y, ac[4 * g + 1], bf_hi(xr[2 * g])));
                x1p[2 * g + 1] = pack2(fmaf(ga.x, ac[4 * g + 2], bf_lo(xr[2 * g + 1])), fmaf(ga.y, ac[4 * g + 3], bf_hi(xr[2 * g + 1])));
                st_relaxed(xo + g * 256, nz(x1p[2 * g])); st_relaxed(xo + g * 256 + 32, nz(x1p[2 * g + 1]));
                mma1688(ds, x1p[2 * g], x1p[2 * g + 1], 0x3F803F80u);
                mma1688(da, x1p[2 * g], x1p[2 * g + 1], x1p[2 * g]);
                mma1688(db, x1p[2 * g], x1p[2 * g + 1], x1p[2 * g + 1]);
            }
            const int src = (lane & ~3) | (lr >> 1);
            const float qa = __shfl_sync(~0u, (lr & 1) ? da[1] : da[0], src), qb = __shfl_sync(~0u, (lr & 1) ? db[3] : db[2], src);
            const float kk = (q & 1) ? ((q & 2) ? qb : qa) : ((q & 2) ? ds[2] : ds[0]);
            st_relaxed(act + RB_ST + ((tile * 8 + j) * 64 + 16 * wi + lr + 4 * (q & 2)) * 2 + (q & 1), nz(__float_as_uint(kk)));
            __syncwarp();
            if (lane < 2) mbar_arrive(BAR(B_PUB + 4 + w));
        }
        PROFC(15);
        uint32_t h2a[32], h2b[24];
        {
            const int fa = pass_f(fs, 0), fb = pass_f(fs, 1), fc = pass_f(fs, 2);
            uint32_t* h2g = act + RB_H2 + (8 * w + 2 * wi) * 32 + lane;
            const uint32_t a0 = mkdesc(sb + OFF_Y + w * HALF, DT);
            {
                LnRow ca, cb;
                {
                    const uint32_t* sg = act + RB_ST + ((tile * 8 + 2 * q) * 64 + 16 * wi + lr) * 2;
                    uint2 u[4];
                    WAIT(B_FULLV + w, 1);
                    PROFC(16);
#pragma unroll
                    for (int i = 0; i < 4; i++) { const float2 v = lds2f(sb + OFF_X + X_STAT + w * 49152 + ((2 * q + (i >> 1)) * 64 + 16 * wi + lr + 8 * (i & 1)) * 8); u[i] = make_uint2(__float_as_uint(v.x), __float_as_uint(v.y)); }
                    while (__any_sync(~0u, min(min(min(u[0].x, u[0].y), min(u[1].x, u[1].y)), min(min(u[2].x, u[2].y), min(u[3].x, u[3].y))) == 0u)) {
#pragma unroll
                        for (int i = 0; i < 4; i++) u[i] = ld_relaxed2(sg + (i >> 1) * 128 + (i & 1) * 16);
                    }
                    warp_arrive(BAR(B_EMPTY + 3 + 3 * w));
                    float v[4] = {__uint_as_float(u[0].x) + __uint_as_float(u[2].x), __uint_as_float(u[0].y) + __uint_as_float(u[2].y),
                                  __uint_as_float(u[1].x) + __uint_as_float(u[3].x), __uint_as_float(u[1].y) + __uint_as_float(u[3].y)};
#pragma unroll
                    for (int i = 0; i < 4; i++) { v[i] += __shfl_xor_sync(~0u, v[i], 1); v[i] += __shfl_xor_sync(~0u, v[i], 2); }
                    ca = ln_coeffs(v[0] * (1.f / DM), v[1] * (1.f / DM));
                    cb = ln_coeffs(v[2] * (1.f / DM), v[3] * (1.f / DM));
                }
                const uint32_t ha = sb + OFF_Y + w * HALF + (lane >> 4) * 1024 + (2 * wi + ((lane >> 3) & 1)) * 128 + (lane & 7) * 16;
                const uint32_t sta = sb + M_ST + q * 16;
                const uint32_t* xg = act + RB_X1 + tile * 14336 + (lane >> 4) * 256 + wi * 64 + (lane & 15) * 4;
                uint32_t x[8];
                const uint32_t xs = sb + OFF_Y + w * HALF + (lane >> 4) * 1024 + wi * 256 + (lane & 15) * 16;
                uint4 st[2];
                auto load = [&](int s) {
                    if (s == 4) mbar_wait_c(BAR(B_XFULL + 4 + w), 1);
                    ldsm4(ha + s * 4096, x); ldsm4(ha + s * 4096 + 2048, x + 4);
                    st[0] = lds4(sta + s * 128); st[1] = lds4(sta + s * 128 + 64);
                };
                auto prep = [&](int s, uint32_t* f) {
                    if (__any_sync(~0u, min(min(min(x[0], x[1]), min(x[2], x[3])), min(min(x[4], x[5]), min(x[6], x[7]))) == 0u)) {
                        WG_WAIT(0);
                        x1_fix(xg, xs, s);
                        ldsm4(ha + s * 4096, x); ldsm4(ha + s * 4096 + 2048, x + 4);
                    }
#pragma unroll
                    for (int i = 0; i < 2; i++) {
                        f[4 * i] = ln_mod(ln_norm(x[4 * i], ca), st[i].x, st[i].y); f[4 * i + 1] = ln_mod(ln_norm(x[4 * i + 1], cb), st[i].x, st[i].y);
                        f[4 * i + 2] = ln_mod(ln_norm(x[4 * i + 2], ca), st[i].z, st[i].w); f[4 * i + 3] = ln_mod(ln_norm(x[4 * i + 3], cb), st[i].z, st[i].w);
                    }
                    if (s < 13) load(s + 1);
                    stsm4(ha + s * 4096, f[0], f[1], f[2], f[3]); stsm4(ha + s * 4096 + 2048, f[4], f[5], f[6], f[7]);
                };
                float ac[128];
                uint32_t fr[3][8];
                uint64_t bd = (DB128 & ~0xFFFFFFFFull) | mkdesc(sb, DB128);
                reg_def<128>(ac);
                WAIT(B_GFULL + 2 + w, 0);
                load(0);
                prep(0, fr[0]);
                PROFC(17);
#pragma unroll
                for (int s = 0; s < 14; s++) {
                    const uint32_t* f = fr[s % 3];
                    WAIT(B_FULL + g1_slot(s), s >= 7);
                    WG_FENCE();
                    wgmma_rl_256(ac, f[0], f[1], f[2], f[3], bd, s != 0);
                    wgmma_rl_256(ac, f[4], f[5], f[6], f[7], bd + 128, 1);
                    bd += s == 6 ? p.zero - 6 * 1024ull : 1024;
                    WG_COMMIT();
                    if (s < 13) prep(s + 1, fr[(s + 1) % 3]);
                    if (s > 0) { WG_WAIT(1); warp_arrive(BAR(B_EMPTY + g1_slot(s - 1))); }
                }
                fence_async_smem();
                PROFC(18);
                WG_WAIT(0);
                reg_fence<128>(ac);
                warp_arrive(BAR(B_EMPTY + 6));
#pragma unroll
                for (int g = 0; g < 16; g++) {
                    h2a[2 * g] = hmul2(pack2_relu(ac[4 * g], ac[4 * g + 1]), pack2(ac[64 + 4 * g], ac[64 + 4 * g + 1]));
                    h2a[2 * g + 1] = hmul2(pack2_relu(ac[4 * g + 2], ac[4 * g + 3]), pack2(ac[64 + 4 * g + 2], ac[64 + 4 * g + 3]));
                }
                bar_sync(1 + w, 128);
            }
            PROFC(19);
            {
                float ac[64];
                reg_def<64>(ac);
                const uint32_t bx = mkdesc(sb, dconst(8192, 1024, 1));
#pragma unroll 1
                for (int s = 0; s < 7; s++) {
                    WAIT(B_FULL + s, 0);
                    const uint32_t ad = a0 + s * 512, bd = bx + (slot_off(s) >> 4);
                    WG_FENCE();
#pragma unroll
                    for (int k = 0; k < 4; k++) wgmma_ss_128<DT, DB128>(ac, ad + k * 128, bd + k * 128, (s | k) != 0);
                    WG_COMMIT();
                    if (s == 1) {
#pragma unroll
                        for (int g = 0; g < 16; g++) { h2g[(fa / 8 + g) * 512] = h2a[2 * g]; h2g[(fa / 8 + g) * 512 + 32] = h2a[2 * g + 1]; }
                        warp_arrive(BAR(B_PUB + 6));
                    }
                    if (s > 0) { WG_WAIT(1); warp_arrive(BAR(B_EMPTY + s - 1)); }
                }
                WG_WAIT(0);
                reg_fence<64>(ac);
                warp_arrive(BAR(B_EMPTY + 6));
#pragma unroll
                for (int g = 0; g < 8; g++) {
                    h2b[2 * g] = hmul2(pack2_relu(ac[4 * g], ac[4 * g + 1]), pack2(ac[32 + 4 * g], ac[32 + 4 * g + 1]));
                    h2b[2 * g + 1] = hmul2(pack2_relu(ac[4 * g + 2], ac[4 * g + 3]), pack2(ac[32 + 4 * g + 2], ac[32 + 4 * g + 3]));
                }
            }
            PROFC(27);
            {
                float ac[32];
                reg_def<32>(ac);
                const uint32_t bx = mkdesc(sb, dconst(4096, 512, 2));
#pragma unroll 1
                for (int s = 0; s < 7; s++) {
                    WAIT(B_FULL + s, 1);
                    const uint32_t ad = a0 + s * 512, bd = bx + (slot_off(s) >> 4);
                    WG_FENCE();
#pragma unroll
                    for (int k = 0; k < 4; k++) wgmma_ss_64<DT, dconst(4096, 512, 2)>(ac, ad + k * 128, bd + k * 64, (s | k) != 0);
                    WG_COMMIT();
                    if (s == 1) {
#pragma unroll
                        for (int g = 0; g < 8; g++) { h2g[(fb / 8 + g) * 512] = h2b[2 * g]; h2g[(fb / 8 + g) * 512 + 32] = h2b[2 * g + 1]; }
                        warp_arrive(BAR(B_PUB + 7));
                    }
                    if (s > 0) { WG_WAIT(1); warp_arrive(BAR(B_EMPTY + s - 1)); }
                }
                WG_WAIT(0);
                reg_fence<32>(ac);
                __syncwarp();
                if (lane < 6) mbar_arrive(BAR(B_EMPTY + 6 + lane));
                PROFC(20);
#pragma unroll
                for (int g = 0; g < 4; g++) {
                    h2b[16 + 2 * g] = hmul2(pack2_relu(ac[4 * g], ac[4 * g + 1]), pack2(ac[16 + 4 * g], ac[16 + 4 * g + 1]));
                    h2b[16 + 2 * g + 1] = hmul2(pack2_relu(ac[4 * g + 2], ac[4 * g + 3]), pack2(ac[16 + 4 * g + 2], ac[16 + 4 * g + 3]));
                    h2g[(fc / 8 + g) * 512] = h2b[16 + 2 * g]; h2g[(fc / 8 + g) * 512 + 32] = h2b[16 + 2 * g + 1];
                }
                warp_arrive(BAR(B_PUB + 8));
                asm volatile("barrier.cluster.wait.aligned;" ::: "memory");
                if (lane == 0) {
                    uint32_t rb;
                    asm volatile("mapa.shared::cluster.u32 %0, %1, %2;" : "=r"(rb) : "r"(BAR(B_PEER)), "r"(kh ^ 1));
                    asm volatile("mbarrier.arrive.relaxed.cluster.shared::cluster.b64 _, [%0];" ::"r"(rb) : "memory");
                }
            }
        }
        PROFC(21);
        {
            float ac[56];
            reg_def<56>(ac);
            constexpr uint64_t DAN = dconst(2048, 128, 0);
            constexpr uint64_t DW = dconst(128, 512, 0);
            const uint32_t bx = mkdesc(sb, DW);
#pragma unroll
            for (int e = 0; e < 4; e++) {
                WAIT(B_FULL + e, 0);
                const uint64_t bd = ((DW & ~0xFFFFFFFFull) | bx) + (slot_off(e) >> 4);
                const uint32_t* hh = e < 2 ? h2a + 16 * e : h2b + 16 * (e - 2);
                WG_FENCE();
#pragma unroll
                for (int k = 0; k < (e < 3 ? 4 : 2); k++) wgmma_rl_112(ac, hh[4 * k], hh[4 * k + 1], hh[4 * k + 2], hh[4 * k + 3], bd + (k >> 1) * 512 + (k & 1) * 16, (e | k) != 0);
                WG_COMMIT();
                if (e > 0) { WG_WAIT(1); warp_arrive(BAR(B_EMPTY + e - 1)); }
            }
            PROFC(22);
            uint32_t ad = mkdesc(sb + 4 * 16384 + 8192 + w * 1024, DAN), bd = bx + 4 * 1024, fb_ = BAR(B_FULL + 4), eb_ = BAR(B_EMPTY + 3), par = 0;
#pragma unroll 1
            for (int e = 4; e < 25; e++) {
                mbar_wait_c(fb_, par);
                WG_FENCE();
                wgmma_ss_112<DAN, DW>(ac, ad, bd, 1);
                wgmma_ss_112<DAN, DW>(ac, ad + 256, bd + 16, 1);
                WG_COMMIT();
                WG_WAIT(1);
                warp_arrive(eb_);
                eb_ = fb_ + 8 * (B_EMPTY - B_FULL);
                ad += 1024; bd += 1024; fb_ += 8;
                if (e == 11 || e == 23) { ad -= 12 * 1024; bd -= 12 * 1024; fb_ -= 96; par ^= 1; }
            }
            mbar_wait_cluster(BAR(B_PEER), 0);
            WG_WAIT(0);
            reg_fence<56>(ac);
            PROFC(24);
            uint32_t rdst, rbar;
            asm volatile("mapa.shared::cluster.u32 %0, %1, %2;" : "=r"(rdst) : "r"(sb + OFF_Y + (5 + w) * 16384 + t * 16), "r"(kh ^ 1));
            asm volatile("mapa.shared::cluster.u32 %0, %1, %2;" : "=r"(rbar) : "r"(BAR(B_XCH + w)), "r"(kh ^ 1));
#pragma unroll
            for (int g = 0; g < 3; g++)
                asm volatile("st.async.shared::cluster.mbarrier::complete_tx::bytes.v4.b32 [%0], {%1,%2,%3,%4}, [%5];" ::"r"(rdst + g * 2048),
                             "r"(pack2(ac[28 + 8 * g], ac[29 + 8 * g])), "r"(pack2(ac[30 + 8 * g], ac[31 + 8 * g])), "r"(pack2(ac[32 + 8 * g], ac[33 + 8 * g])),
                             "r"(pack2(ac[34 + 8 * g], ac[35 + 8 * g])), "r"(rbar) : "memory");
            asm volatile("st.async.shared::cluster.mbarrier::complete_tx::bytes.v2.b32 [%0], {%1,%2}, [%3];" ::"r"(rdst + 6144 - t * 8),
                         "r"(pack2(ac[52], ac[53])), "r"(pack2(ac[54], ac[55])), "r"(rbar) : "memory");
            mbar_wait_cluster(BAR(B_XCH + w), 0);
            PROFC(25);
            uint32_t op[14], rv[14];
#pragma unroll
            for (int g = 0; g < 3; g++) *(uint4*)(rv + 4 * g) = *(const uint4*)(smem + OFF_Y + (5 + w) * 16384 + t * 16 + g * 2048);
            *(uint2*)(rv + 12) = *(const uint2*)(smem + OFF_Y + (5 + w) * 16384 + 6144 + t * 8);
#pragma unroll
            for (int i = 0; i < 14; i++) {
                const float2 gb = *(const float2*)(smem + M_G + 224 + (8 * (i >> 1) + 2 * q) * 4);
                op[i] = pack2(fmaf(gb.x, ac[2 * i] + bf_lo(rv[i]), bf_lo(x1p[i])), fmaf(gb.y, ac[2 * i + 1] + bf_hi(rv[i]), bf_hi(x1p[i])));
            }
            WAIT(B_EMPTY + 1, 0);
            const uint32_t oc = sb + OUT_STAGE + warp * 1792;
            const uint32_t oa = oc + (((lane >> 3) & 1) * 8 + (lane & 7)) * 112 + (lane >> 4) * 16;
            stsm4(oa, op[0], op[1], op[2], op[3]); stsm4(oa + 32, op[4], op[5], op[6], op[7]); stsm4(oa + 64, op[8], op[9], op[10], op[11]);
            asm volatile("stmatrix.sync.aligned.m8n8.x2.shared.b16 [%0], {%1,%2};" ::"r"(oa + 96), "r"(op[12]), "r"(op[13]));
            fence_async_smem();
            __syncwarp();
            asm volatile("{\n.reg .pred p;\nelect.sync _|p, 0xffffffff;\n@p cp.async.bulk.tensor.3d.global.shared::cta.bulk_group [%0, {%2, %3, %4}], [%1];\n"
                         "cp.async.bulk.commit_group;\ncp.async.bulk.wait_group.read 0;\n}" ::"l"(&p.om), "r"(oc), "r"(56 * j), "r"(128 * r + 64 * w + 16 * wi), "r"(0) : "memory");
        }
        PROFC(26);
        bar_sync(1 + w, 128);
        if (wi == 0) warp_arrive(BAR(B_DONE));
        return;
    }
    helper_late(p, r, j, warp PROF_ARGS);
}

#undef act
typedef CUresult (*EncodeFn)(CUtensorMap*, CUtensorMapDataType, cuuint32_t, void*, const cuuint64_t*, const cuuint64_t*, const cuuint32_t*,
                             const cuuint32_t*, CUtensorMapInterleave, CUtensorMapSwizzle, CUtensorMapL2promotion, CUtensorMapFloatOOBfill);

static void make_map(EncodeFn fn, CUtensorMap* m, const void* ptr, uint64_t d0, uint64_t d1, uint64_t d2, uint64_t s1, uint64_t s2,
                     uint32_t b0, uint32_t b1, uint32_t b2, CUtensorMapSwizzle sw) {
    cuuint64_t dims[3] = {d0, d1, d2}, strides[2] = {s1, s2};
    cuuint32_t box[3] = {b0, b1, b2}, es[3] = {1, 1, 1};
    CUresult rc = fn(m, CU_TENSOR_MAP_DATA_TYPE_BFLOAT16, 3, (void*)ptr, dims, strides, box, es, CU_TENSOR_MAP_INTERLEAVE_NONE, sw,
                     CU_TENSOR_MAP_L2_PROMOTION_L2_128B, CU_TENSOR_MAP_FLOAT_OOB_FILL_NONE);
    (void)rc;
}

extern "C" void kernel_launch(void* const* d_in, const int* in_sizes, int n_in, void* d_out, int out_size) {
    (void)in_sizes; (void)n_in; (void)out_size;
    static EncodeFn fn = nullptr;
    static uint32_t* act_base = nullptr;
    if (!fn) {
        cudaDriverEntryPointQueryResult st;
        cudaGetDriverEntryPoint("cuTensorMapEncodeTiled", (void**)&fn, cudaEnableDefault, &st);
        void* a = nullptr;
        cudaGetSymbolAddress(&a, g_act);
        act_base = (uint32_t*)(((uintptr_t)a + 0xFFFFF) & ~(uintptr_t)0xFFFFF);
        cudaFuncSetAttribute(fused_block_kernel, cudaFuncAttributeMaxDynamicSharedMemorySize, SMEM_BYTES);
    }
    Params p;
    p.x = (const bf16*)d_in[0];
    const bf16* wqkv = (const bf16*)d_in[1];
    p.wqkv = wqkv;
    p.wop = (const bf16*)d_in[2];
    p.wg = (const bf16*)d_in[4];
    p.wu = (const bf16*)d_in[5];
    p.wd = (const bf16*)d_in[6];
    p.c = (const bf16*)d_in[7];
    p.wmod = (const bf16*)d_in[8];
    p.out = (bf16*)d_out;
    p.zero = 0;
    p.actb = act_base;
    make_map(fn, &p.wm, p.wmod, 2688, 448, 1, 5376, 5376 * 448, 16, 224, 1, CU_TENSOR_MAP_SWIZZLE_NONE);
    make_map(fn, &p.wm2, p.wmod, 2688, 448, 1, 5376, 5376 * 448, 32, 224, 1, CU_TENSOR_MAP_SWIZZLE_NONE);
    make_map(fn, &p.om, p.out, 448, 2048, 1, 896, 896 * 2048, 56, 16, 1, CU_TENSOR_MAP_SWIZZLE_NONE);
    make_map(fn, &p.xm, p.x, 448, 2048, 1, 896, 896 * 2048, 64, 128, 1, CU_TENSOR_MAP_SWIZZLE_128B);
    make_map(fn, &p.qkv, wqkv, 1344, 448, 1, 2688, 2688 * 448, 64, 224, 1, CU_TENSOR_MAP_SWIZZLE_128B);
    make_map(fn, &p.wo, p.wop, 448, 448, 1, 896, 896 * 448, 64, 224, 1, CU_TENSOR_MAP_SWIZZLE_128B);
    make_map(fn, &p.ga, p.wg, 64, 448, 28, 3584, 128, 64, 32, 2, CU_TENSOR_MAP_SWIZZLE_128B);
    make_map(fn, &p.ua, p.wu, 64, 448, 28, 3584, 128, 64, 32, 2, CU_TENSOR_MAP_SWIZZLE_128B);
    make_map(fn, &p.gb, p.wg, 64, 448, 28, 3584, 128, 64, 64, 1, CU_TENSOR_MAP_SWIZZLE_128B);
    make_map(fn, &p.ub, p.wu, 64, 448, 28, 3584, 128, 64, 64, 1, CU_TENSOR_MAP_SWIZZLE_128B);
    make_map(fn, &p.gc, p.wg, 32, 448, 56, 3584, 64, 32, 64, 1, CU_TENSOR_MAP_SWIZZLE_64B);
    make_map(fn, &p.uc, p.wu, 32, 448, 56, 3584, 64, 32, 64, 1, CU_TENSOR_MAP_SWIZZLE_64B);
    make_map(fn, &p.dn, p.wd, 8, 1792, 56, 896, 16, 8, 32, 7, CU_TENSOR_MAP_SWIZZLE_NONE);
    fused_block_kernel<<<NCTA, 384, SMEM_BYTES>>>(p);
}
```

```cpp
#include <cuda_runtime.h>
#include <cuda_bf16.h>
#include <cuda.h>
#include <stdint.h>

typedef __nv_bfloat16 bf16;

template<uint64_t CA, uint64_t CB> __device__ __forceinline__ void wgmma_sk_160(float* d, uint32_t da, uint32_t db, int sd) {
  asm volatile("{\n.reg .pred p;\n.reg .b64 a, b;\nsetp.ne.b32 p, %82, 0;\nmov.b64 a, {%80, %83};\nmov.b64 b, {%81, %84};\n"
    "wgmma.mma_async.sync.aligned.m64n160k16.f32.bf16.bf16 {%0,%1,%2,%3,%4,%5,%6,%7,%8,%9,%10,%11,%12,%13,%14,%15,%16,%17,%18,%19,%20,%21,%22,%23,%24,%25,%26,%27,%28,%29,%30,%31,%32,%33,%34,%35,%36,%37,%38,%39,%40,%41,%42,%43,%44,%45,%46,%47,%48,%49,%50,%51,%52,%53,%54,%55,%56,%57,%58,%59,%60,%61,%62,%63,%64,%65,%66,%67,%68,%69,%70,%71,%72,%73,%74,%75,%76,%77,%78,%79}, a, b, p, 1, 1, 0, 0;\n}\n"
    : "+f"(d[0]),"+f"(d[1]),"+f"(d[2]),"+f"(d[3]),"+f"(d[4]),"+f"(d[5]),"+f"(d[6]),"+f"(d[7]),"+f"(d[8]),"+f"(d[9]),"+f"(d[10]),"+f"(d[11]),"+f"(d[12]),"+f"(d[13]),"+f"(d[14]),"+f"(d[15]),"+f"(d[16]),"+f"(d[17]),"+f"(d[18]),"+f"(d[19]),"+f"(d[20]),"+f"(d[21]),"+f"(d[22]),"+f"(d[23]),"+f"(d[24]),"+f"(d[25]),"+f"(d[26]),"+f"(d[27]),"+f"(d[28]),"+f"(d[29]),"+f"(d[30]),"+f"(d[31]),"+f"(d[32]),"+f"(d[33]),"+f"(d[34]),"+f"(d[35]),"+f"(d[36]),"+f"(d[37]),"+f"(d[38]),"+f"(d[39]),"+f"(d[40]),"+f"(d[41]),"+f"(d[42]),"+f"(d[43]),"+f"(d[44]),"+f"(d[45]),"+f"(d[46]),"+f"(d[47]),"+f"(d[48]),"+f"(d[49]),"+f"(d[50]),"+f"(d[51]),"+f"(d[52]),"+f"(d[53]),"+f"(d[54]),"+f"(d[55]),"+f"(d[56]),"+f"(d[57]),"+f"(d[58]),"+f"(d[59]),"+f"(d[60]),"+f"(d[61]),"+f"(d[62]),"+f"(d[63]),"+f"(d[64]),"+f"(d[65]),"+f"(d[66]),"+f"(d[67]),"+f"(d[68]),"+f"(d[69]),"+f"(d[70]),"+f"(d[71]),"+f"(d[72]),"+f"(d[73]),"+f"(d[74]),"+f"(d[75]),"+f"(d[76]),"+f"(d[77]),"+f"(d[78]),"+f"(d[79])
    : "r"(da), "r"(db), "r"(sd), "n"((uint32_t)(CA >> 32)), "n"((uint32_t)(CB >> 32)));
}
__device__ __forceinline__ void wgmma_rl_56(float* d, uint32_t a0, uint32_t a1, uint32_t a2, uint32_t a3, uint64_t db, int sd) {
  asm volatile("{\n.reg .pred p;\nsetp.ne.b32 p, %33, 0;\n"
    "wgmma.mma_async.sync.aligned.m64n56k16.f32.bf16.bf16 {%0,%1,%2,%3,%4,%5,%6,%7,%8,%9,%10,%11,%12,%13,%14,%15,%16,%17,%18,%19,%20,%21,%22,%23,%24,%25,%26,%27}, {%28,%29,%30,%31}, %32, p, 1, 1, 1;\n}\n"
    : "+f"(d[0]),"+f"(d[1]),"+f"(d[2]),"+f"(d[3]),"+f"(d[4]),"+f"(d[5]),"+f"(d[6]),"+f"(d[7]),"+f"(d[8]),"+f"(d[9]),"+f"(d[10]),"+f"(d[11]),"+f"(d[12]),"+f"(d[13]),"+f"(d[14]),"+f"(d[15]),"+f"(d[16]),"+f"(d[17]),"+f"(d[18]),"+f"(d[19]),"+f"(d[20]),"+f"(d[21]),"+f"(d[22]),"+f"(d[23]),"+f"(d[24]),"+f"(d[25]),"+f"(d[26]),"+f"(d[27])
    : "r"(a0), "r"(a1), "r"(a2), "r"(a3), "l"(db), "r"(sd));
}
template<uint64_t CA, uint64_t CB> __device__ __forceinline__ void wgmma_ss_56(float* d, uint32_t da, uint32_t db, int sd) {
  asm volatile("{\n.reg .pred p;\n.reg .b64 a, b;\nsetp.ne.b32 p, %30, 0;\nmov.b64 a, {%28, %31};\nmov.b64 b, {%29, %32};\n"
    "wgmma.mma_async.sync.aligned.m64n56k16.f32.bf16.bf16 {%0,%1,%2,%3,%4,%5,%6,%7,%8,%9,%10,%11,%12,%13,%14,%15,%16,%17,%18,%19,%20,%21,%22,%23,%24,%25,%26,%27}, a, b, p, 1, 1, 0, 1;\n}\n"
    : "+f"(d[0]),"+f"(d[1]),"+f"(d[2]),"+f"(d[3]),"+f"(d[4]),"+f"(d[5]),"+f"(d[6]),"+f"(d[7]),"+f"(d[8]),"+f"(d[9]),"+f"(d[10]),"+f"(d[11]),"+f"(d[12]),"+f"(d[13]),"+f"(d[14]),"+f"(d[15]),"+f"(d[16]),"+f"(d[17]),"+f"(d[18]),"+f"(d[19]),"+f"(d[20]),"+f"(d[21]),"+f"(d[22]),"+f"(d[23]),"+f"(d[24]),"+f"(d[25]),"+f"(d[26]),"+f"(d[27])
    : "r"(da), "r"(db), "r"(sd), "n"((uint32_t)(CA >> 32)), "n"((uint32_t)(CB >> 32)));
}
__device__ __forceinline__ void wgmma_rl_256(float* d, uint32_t a0, uint32_t a1, uint32_t a2, uint32_t a3, uint64_t db, int sd) {
  asm volatile("{\n.reg .pred p;\nsetp.ne.b32 p, %133, 0;\n"
    "wgmma.mma_async.sync.aligned.m64n256k16.f32.bf16.bf16 {%0,%1,%2,%3,%4,%5,%6,%7,%8,%9,%10,%11,%12,%13,%14,%15,%16,%17,%18,%19,%20,%21,%22,%23,%24,%25,%26,%27,%28,%29,%30,%31,%32,%33,%34,%35,%36,%37,%38,%39,%40,%41,%42,%43,%44,%45,%46,%47,%48,%49,%50,%51,%52,%53,%54,%55,%56,%57,%58,%59,%60,%61,%62,%63,%64,%65,%66,%67,%68,%69,%70,%71,%72,%73,%74,%75,%76,%77,%78,%79,%80,%81,%82,%83,%84,%85,%86,%87,%88,%89,%90,%91,%92,%93,%94,%95,%96,%97,%98,%99,%100,%101,%102,%103,%104,%105,%106,%107,%108,%109,%110,%111,%112,%113,%114,%115,%116,%117,%118,%119,%120,%121,%122,%123,%124,%125,%126,%127}, {%128,%129,%130,%131}, %132, p, 1, 1, 1;\n}\n"
    : "+f"(d[0]),"+f"(d[1]),"+f"(d[2]),"+f"(d[3]),"+f"(d[4]),"+f"(d[5]),"+f"(d[6]),"+f"(d[7]),"+f"(d[8]),"+f"(d[9]),"+f"(d[10]),"+f"(d[11]),"+f"(d[12]),"+f"(d[13]),"+f"(d[14]),"+f"(d[15]),"+f"(d[16]),"+f"(d[17]),"+f"(d[18]),"+f"(d[19]),"+f"(d[20]),"+f"(d[21]),"+f"(d[22]),"+f"(d[23]),"+f"(d[24]),"+f"(d[25]),"+f"(d[26]),"+f"(d[27]),"+f"(d[28]),"+f"(d[29]),"+f"(d[30]),"+f"(d[31]),"+f"(d[32]),"+f"(d[33]),"+f"(d[34]),"+f"(d[35]),"+f"(d[36]),"+f"(d[37]),"+f"(d[38]),"+f"(d[39]),"+f"(d[40]),"+f"(d[41]),"+f"(d[42]),"+f"(d[43]),"+f"(d[44]),"+f"(d[45]),"+f"(d[46]),"+f"(d[47]),"+f"(d[48]),"+f"(d[49]),"+f"(d[50]),"+f"(d[51]),"+f"(d[52]),"+f"(d[53]),"+f"(d[54]),"+f"(d[55]),"+f"(d[56]),"+f"(d[57]),"+f"(d[58]),"+f"(d[59]),"+f"(d[60]),"+f"(d[61]),"+f"(d[62]),"+f"(d[63]),"+f"(d[64]),"+f"(d[65]),"+f"(d[66]),"+f"(d[67]),"+f"(d[68]),"+f"(d[69]),"+f"(d[70]),"+f"(d[71]),"+f"(d[72]),"+f"(d[73]),"+f"(d[74]),"+f"(d[75]),"+f"(d[76]),"+f"(d[77]),"+f"(d[78]),"+f"(d[79]),"+f"(d[80]),"+f"(d[81]),"+f"(d[82]),"+f"(d[83]),"+f"(d[84]),"+f"(d[85]),"+f"(d[86]),"+f"(d[87]),"+f"(d[88]),"+f"(d[89]),"+f"(d[90]),"+f"(d[91]),"+f"(d[92]),"+f"(d[93]),"+f"(d[94]),"+f"(d[95]),"+f"(d[96]),"+f"(d[97]),"+f"(d[98]),"+f"(d[99]),"+f"(d[100]),"+f"(d[101]),"+f"(d[102]),"+f"(d[103]),"+f"(d[104]),"+f"(d[105]),"+f"(d[106]),"+f"(d[107]),"+f"(d[108]),"+f"(d[109]),"+f"(d[110]),"+f"(d[111]),"+f"(d[112]),"+f"(d[113]),"+f"(d[114]),"+f"(d[115]),"+f"(d[116]),"+f"(d[117]),"+f"(d[118]),"+f"(d[119]),"+f"(d[120]),"+f"(d[121]),"+f"(d[122]),"+f"(d[123]),"+f"(d[124]),"+f"(d[125]),"+f"(d[126]),"+f"(d[127])
    : "r"(a0), "r"(a1), "r"(a2), "r"(a3), "l"(db), "r"(sd));
}
template<uint64_t CA, uint64_t CB> __device__ __forceinline__ void wgmma_ss_128(float* d, uint32_t da, uint32_t db, int sd) {
  asm volatile("{\n.reg .pred p;\n.reg .b64 a, b;\nsetp.ne.b32 p, %66, 0;\nmov.b64 a, {%64, %67};\nmov.b64 b, {%65, %68};\n"
    "wgmma.mma_async.sync.aligned.m64n128k16.f32.bf16.bf16 {%0,%1,%2,%3,%4,%5,%6,%7,%8,%9,%10,%11,%12,%13,%14,%15,%16,%17,%18,%19,%20,%21,%22,%23,%24,%25,%26,%27,%28,%29,%30,%31,%32,%33,%34,%35,%36,%37,%38,%39,%40,%41,%42,%43,%44,%45,%46,%47,%48,%49,%50,%51,%52,%53,%54,%55,%56,%57,%58,%59,%60,%61,%62,%63}, a, b, p, 1, 1, 0, 1;\n}\n"
    : "+f"(d[0]),"+f"(d[1]),"+f"(d[2]),"+f"(d[3]),"+f"(d[4]),"+f"(d[5]),"+f"(d[6]),"+f"(d[7]),"+f"(d[8]),"+f"(d[9]),"+f"(d[10]),"+f"(d[11]),"+f"(d[12]),"+f"(d[13]),"+f"(d[14]),"+f"(d[15]),"+f"(d[16]),"+f"(d[17]),"+f"(d[18]),"+f"(d[19]),"+f"(d[20]),"+f"(d[21]),"+f"(d[22]),"+f"(d[23]),"+f"(d[24]),"+f"(d[25]),"+f"(d[26]),"+f"(d[27]),"+f"(d[28]),"+f"(d[29]),"+f"(d[30]),"+f"(d[31]),"+f"(d[32]),"+f"(d[33]),"+f"(d[34]),"+f"(d[35]),"+f"(d[36]),"+f"(d[37]),"+f"(d[38]),"+f"(d[39]),"+f"(d[40]),"+f"(d[41]),"+f"(d[42]),"+f"(d[43]),"+f"(d[44]),"+f"(d[45]),"+f"(d[46]),"+f"(d[47]),"+f"(d[48]),"+f"(d[49]),"+f"(d[50]),"+f"(d[51]),"+f"(d[52]),"+f"(d[53]),"+f"(d[54]),"+f"(d[55]),"+f"(d[56]),"+f"(d[57]),"+f"(d[58]),"+f"(d[59]),"+f"(d[60]),"+f"(d[61]),"+f"(d[62]),"+f"(d[63])
    : "r"(da), "r"(db), "r"(sd), "n"((uint32_t)(CA >> 32)), "n"((uint32_t)(CB >> 32)));
}
template<uint64_t CA, uint64_t CB> __device__ __forceinline__ void wgmma_ss_64(float* d, uint32_t da, uint32_t db, int sd) {
  asm volatile("{\n.reg .pred p;\n.reg .b64 a, b;\nsetp.ne.b32 p, %34, 0;\nmov.b64 a, {%32, %35};\nmov.b64 b, {%33, %36};\n"
    "wgmma.mma_async.sync.aligned.m64n64k16.f32.bf16.bf16 {%0,%1,%2,%3,%4,%5,%6,%7,%8,%9,%10,%11,%12,%13,%14,%15,%16,%17,%18,%19,%20,%21,%22,%23,%24,%25,%26,%27,%28,%29,%30,%31}, a, b, p, 1, 1, 0, 1;\n}\n"
    : "+f"(d[0]),"+f"(d[1]),"+f"(d[2]),"+f"(d[3]),"+f"(d[4]),"+f"(d[5]),"+f"(d[6]),"+f"(d[7]),"+f"(d[8]),"+f"(d[9]),"+f"(d[10]),"+f"(d[11]),"+f"(d[12]),"+f"(d[13]),"+f"(d[14]),"+f"(d[15]),"+f"(d[16]),"+f"(d[17]),"+f"(d[18]),"+f"(d[19]),"+f"(d[20]),"+f"(d[21]),"+f"(d[22]),"+f"(d[23]),"+f"(d[24]),"+f"(d[25]),"+f"(d[26]),"+f"(d[27]),"+f"(d[28]),"+f"(d[29]),"+f"(d[30]),"+f"(d[31])
    : "r"(da), "r"(db), "r"(sd), "n"((uint32_t)(CA >> 32)), "n"((uint32_t)(CB >> 32)));
}
template<uint64_t CA, uint64_t CB> __device__ __forceinline__ void wgmma_ss_112(float* d, uint32_t da, uint32_t db, int sd) {
  asm volatile("{\n.reg .pred p;\n.reg .b64 a, b;\nsetp.ne.b32 p, %58, 0;\nmov.b64 a, {%56, %59};\nmov.b64 b, {%57, %60};\n"
    "wgmma.mma_async.sync.aligned.m64n112k16.f32.bf16.bf16 {%0,%1,%2,%3,%4,%5,%6,%7,%8,%9,%10,%11,%12,%13,%14,%15,%16,%17,%18,%19,%20,%21,%22,%23,%24,%25,%26,%27,%28,%29,%30,%31,%32,%33,%34,%35,%36,%37,%38,%39,%40,%41,%42,%43,%44,%45,%46,%47,%48,%49,%50,%51,%52,%53,%54,%55}, a, b, p, 1, 1, 0, 1;\n}\n"
    : "+f"(d[0]),"+f"(d[1]),"+f"(d[2]),"+f"(d[3]),"+f"(d[4]),"+f"(d[5]),"+f"(d[6]),"+f"(d[7]),"+f"(d[8]),"+f"(d[9]),"+f"(d[10]),"+f"(d[11]),"+f"(d[12]),"+f"(d[13]),"+f"(d[14]),"+f"(d[15]),"+f"(d[16]),"+f"(d[17]),"+f"(d[18]),"+f"(d[19]),"+f"(d[20]),"+f"(d[21]),"+f"(d[22]),"+f"(d[23]),"+f"(d[24]),"+f"(d[25]),"+f"(d[26]),"+f"(d[27]),"+f"(d[28]),"+f"(d[29]),"+f"(d[30]),"+f"(d[31]),"+f"(d[32]),"+f"(d[33]),"+f"(d[34]),"+f"(d[35]),"+f"(d[36]),"+f"(d[37]),"+f"(d[38]),"+f"(d[39]),"+f"(d[40]),"+f"(d[41]),"+f"(d[42]),"+f"(d[43]),"+f"(d[44]),"+f"(d[45]),"+f"(d[46]),"+f"(d[47]),"+f"(d[48]),"+f"(d[49]),"+f"(d[50]),"+f"(d[51]),"+f"(d[52]),"+f"(d[53]),"+f"(d[54]),"+f"(d[55])
    : "r"(da), "r"(db), "r"(sd), "n"((uint32_t)(CA >> 32)), "n"((uint32_t)(CB >> 32)));
}
__device__ __forceinline__ void wgmma_rl_112(float* d, uint32_t a0, uint32_t a1, uint32_t a2, uint32_t a3, uint64_t db, int sd) {
  asm volatile("{\n.reg .pred p;\nsetp.ne.b32 p, %61, 0;\n"
    "wgmma.mma_async.sync.aligned.m64n112k16.f32.bf16.bf16 {%0,%1,%2,%3,%4,%5,%6,%7,%8,%9,%10,%11,%12,%13,%14,%15,%16,%17,%18,%19,%20,%21,%22,%23,%24,%25,%26,%27,%28,%29,%30,%31,%32,%33,%34,%35,%36,%37,%38,%39,%40,%41,%42,%43,%44,%45,%46,%47,%48,%49,%50,%51,%52,%53,%54,%55}, {%56,%57,%58,%59}, %60, p, 1, 1, 1;\n}\n"
    : "+f"(d[0]),"+f"(d[1]),"+f"(d[2]),"+f"(d[3]),"+f"(d[4]),"+f"(d[5]),"+f"(d[6]),"+f"(d[7]),"+f"(d[8]),"+f"(d[9]),"+f"(d[10]),"+f"(d[11]),"+f"(d[12]),"+f"(d[13]),"+f"(d[14]),"+f"(d[15]),"+f"(d[16]),"+f"(d[17]),"+f"(d[18]),"+f"(d[19]),"+f"(d[20]),"+f"(d[21]),"+f"(d[22]),"+f"(d[23]),"+f"(d[24]),"+f"(d[25]),"+f"(d[26]),"+f"(d[27]),"+f"(d[28]),"+f"(d[29]),"+f"(d[30]),"+f"(d[31]),"+f"(d[32]),"+f"(d[33]),"+f"(d[34]),"+f"(d[35]),"+f"(d[36]),"+f"(d[37]),"+f"(d[38]),"+f"(d[39]),"+f"(d[40]),"+f"(d[41]),"+f"(d[42]),"+f"(d[43]),"+f"(d[44]),"+f"(d[45]),"+f"(d[46]),"+f"(d[47]),"+f"(d[48]),"+f"(d[49]),"+f"(d[50]),"+f"(d[51]),"+f"(d[52]),"+f"(d[53]),"+f"(d[54]),"+f"(d[55])
    : "r"(a0), "r"(a1), "r"(a2), "r"(a3), "l"(db), "r"(sd));
}

constexpr int DM = 448;
constexpr int NCTA = 128;
#define WIN 5
#define NPRE 14
#define VPRE 3
constexpr int SPIN_LIMIT = 1 << 22;

constexpr uint32_t OFF_X = 0, OFF_Y = 114688, OFF_MISC = 229376, SMEM_BYTES = 232448;
constexpr uint32_t Y_VR = 0, Y_K = 28672, Y_KOWN = 57344, Y_VOWN = 71680, Y_Q = 86016;
constexpr uint32_t HALF = 57344;
constexpr uint32_t X_STAT = 49152;
constexpr uint32_t OUT_STAGE = 16384;
constexpr uint32_t M_BAR = OFF_MISC;
constexpr uint32_t M_ST = OFF_MISC + 512;
constexpr uint32_t M_G = OFF_MISC + 2304;
constexpr uint32_t M_EPOCH = OFF_MISC + 3040;
enum { B_XFULL = 0, B_FULLK = 7, B_FULLV = 8, B_FULLQ, B_KRFULL, B_VRFULL, B_WOFULL, B_XCH, B_MOD1 = 15, B_FULL = 16, B_WMFULL = 30,
       B_EMPTY = 32, B_XFREE = B_EMPTY + 12, B_GEMV, B_PEER,
       B_PUB = 47,
       B_WMFREE = 56, B_HRDY, B_GFULL = B_HRDY + 3, B_DONE = 31, B_DUMMY = B_GEMV };

__device__ uint32_t g_ticket;
__device__ __align__(128) uint32_t g_mod[8 * 6 * DM];
__device__ __align__(128) uint32_t g_flag[144 * 192];
constexpr int RB_WORDS = 262144, RB_KV = 0, RB_O = 57344, RB_X1 = 86016, RB_H2 = 143360, RB_ST = 258048;
__device__ __align__(128) uint32_t g_act[17 * RB_WORDS];
__device__ __align__(128) uint32_t g_wd[56 * 4 * 1792];
#define PROFH(id)
#define PROFH1(id)
#define PROFC(id)

struct alignas(64) Params {
    CUtensorMap wm, wm2, om, xm, qkv, wo, ga, ua, gb, ub, gc, uc, dn;
    const bf16 *x, *c, *wqkv, *wmod, *wg, *wu, *wd, *wop;
    bf16* out;
    uint32_t* actb;
    uint32_t zero;
};

__device__ __forceinline__ void mbar_init(uint32_t bar, int cnt) { asm volatile("mbarrier.init.shared::cta.b64 [%0], %1;" ::"r"(bar), "r"(cnt) : "memory"); }
__device__ __forceinline__ void mbar_arrive(uint32_t bar) { asm volatile("mbarrier.arrive.shared::cta.b64 _, [%0];" ::"r"(bar) : "memory"); }
__device__ __forceinline__ void mbar_wait(uint32_t bar, uint32_t parity) {
    uint32_t ok; int n = 0;
    do {
        asm volatile("{\n.reg .pred p;\nmbarrier.try_wait.parity.shared::cta.b64 p, [%1], %2;\nselp.u32 %0, 1, 0, p;\n}" : "=r"(ok) : "r"(bar), "r"(parity) : "memory");
        if (++n > SPIN_LIMIT) __trap();
    } while (!ok);
}
__device__ __forceinline__ void mbar_wait_c(uint32_t bar, uint32_t parity) {
    asm volatile("{\n.reg .pred p;\nWL:\nmbarrier.try_wait.parity.shared::cta.b64 p, [%0], %1, 0x989680;\n@!p bra WL;\n}" ::"r"(bar), "r"(parity) : "memory");
}
__device__ __forceinline__ void mbar_wait_cluster(uint32_t bar, uint32_t parity) {
    asm volatile("{\n.reg .pred p;\nWL:\nmbarrier.try_wait.parity.acquire.cluster.shared::cta.b64 p, [%0], %1, 0x989680;\n@!p bra WL;\n}" ::"r"(bar), "r"(parity) : "memory");
}
__device__ __forceinline__ void warp_arrive(uint32_t bar) {
    __syncwarp();
    asm volatile("{\n.reg .pred p;\nelect.sync _|p, 0xffffffff;\n@p mbarrier.arrive.shared::cta.b64 _, [%0];\n}" ::"r"(bar) : "memory");
}
__device__ __forceinline__ int opaque(int v) { return __shfl_sync(~0u, v, 0); }
__device__ __forceinline__ int fresh_tid() { int v; asm volatile("mov.u32 %0, %%tid.x;" : "=r"(v)); return v; }
__device__ __forceinline__ void bar_sync(int id, int n) { asm volatile("bar.sync %0, %1;" ::"r"(id), "r"(n) : "memory"); }
__device__ __forceinline__ void bar_arrive(int id, int n) { asm volatile("bar.arrive %0, %1;" ::"r"(id), "r"(n) : "memory"); }
__device__ __forceinline__ void fence_async_smem() { asm volatile("fence.proxy.async.shared::cta;" ::: "memory"); }
__device__ __forceinline__ void fence_async_global() { asm volatile("fence.proxy.async.global;" ::: "memory"); }
__device__ __forceinline__ void fence_gpu() { asm volatile("fence.release.gpu;" ::: "memory"); }
__device__ __forceinline__ void expect_e(uint32_t bar, uint32_t bytes) {
    asm volatile("{\n.reg .pred p;\nelect.sync _|p, 0xffffffff;\n@p mbarrier.arrive.expect_tx.shared::cta.b64 _, [%0], %1;\n}" ::"r"(bar), "r"(bytes) : "memory");
}
__device__ __forceinline__ void tma3_e(uint32_t dst, const CUtensorMap* m, int c0, int c1, int c2, uint32_t bar) {
    asm volatile("{\n.reg .pred p;\nelect.sync _|p, 0xffffffff;\n@p cp.async.bulk.tensor.3d.shared::cluster.global.mbarrier::complete_tx::bytes [%0], [%1, {%3, %4, %5}], [%2];\n}"
                 ::"r"(dst), "l"(m), "r"(bar), "r"(c0), "r"(c1), "r"(c2) : "memory");
}
__device__ __forceinline__ void bulk_e(uint32_t dst, const void* src, uint32_t bytes, uint32_t bar) {
    asm volatile("{\n.reg .pred p;\nelect.sync _|p, 0xffffffff;\n@p cp.async.bulk.shared::cluster.global.mbarrier::complete_tx::bytes [%0], [%1], %2, [%3];\n}"
                 ::"r"(dst), "l"(src), "r"(bytes), "r"(bar) : "memory");
}
__device__ __forceinline__ void init_e(uint32_t bar, int cnt) {
    asm volatile("{\n.reg .pred p;\nelect.sync _|p, 0xffffffff;\n@p mbarrier.init.shared::cta.b64 [%0], %1;\n}" ::"r"(bar), "r"(cnt) : "memory");
}
__device__ __forceinline__ void l2_prefetch_e(const void* src, uint32_t bytes) {
    asm volatile("{\n.reg .pred p;\nelect.sync _|p, 0xffffffff;\n@p cp.async.bulk.prefetch.L2.global [%0], %1;\n}" ::"l"(src), "r"(bytes) : "memory");
}
__device__ __forceinline__ uint32_t ld_relaxed(const uint32_t* p) { uint32_t v; asm volatile("ld.relaxed.gpu.global.u32 %0, [%1];" : "=r"(v) : "l"(p) : "memory"); return v; }
__device__ __forceinline__ void st_relaxed(uint32_t* p, uint32_t v) { asm volatile("st.relaxed.gpu.global.u32 [%0], %1;" ::"l"(p), "r"(v) : "memory"); }
__device__ __forceinline__ uint4 ld_relaxed4(const uint4* p) { uint4 v; asm volatile("ld.relaxed.gpu.global.v4.u32 {%0,%1,%2,%3}, [%4];" : "=r"(v.x), "=r"(v.y), "=r"(v.z), "=r"(v.w) : "l"(p) : "memory"); return v; }
__device__ __forceinline__ uint4 lds4(uint32_t a) { uint4 v; asm volatile("ld.shared.v4.u32 {%0,%1,%2,%3}, [%4];" : "=r"(v.x), "=r"(v.y), "=r"(v.z), "=r"(v.w) : "r"(a) : "memory"); return v; }
__device__ __forceinline__ float2 lds2f(uint32_t a) { float2 v; asm volatile("ld.shared.v2.f32 {%0,%1}, [%2];" : "=f"(v.x), "=f"(v.y) : "r"(a) : "memory"); return v; }
__device__ __forceinline__ uint32_t lds1(uint32_t a) { uint32_t v; asm volatile("ld.shared.u32 %0, [%1];" : "=r"(v) : "r"(a) : "memory"); return v; }
__device__ __forceinline__ void sts4(uint32_t a, uint4 v) { asm volatile("st.shared.v4.u32 [%0], {%1,%2,%3,%4};" ::"r"(a), "r"(v.x), "r"(v.y), "r"(v.z), "r"(v.w) : "memory"); }
__device__ __forceinline__ void sts1(uint32_t a, uint32_t v) { asm volatile("st.shared.u32 [%0], %1;" ::"r"(a), "r"(v) : "memory"); }
__device__ __forceinline__ void stsm4(uint32_t a, uint32_t r0, uint32_t r1, uint32_t r2, uint32_t r3) {
    asm volatile("stmatrix.sync.aligned.m8n8.x4.shared.b16 [%0], {%1,%2,%3,%4};" ::"r"(a), "r"(r0), "r"(r1), "r"(r2), "r"(r3));
}
__device__ __forceinline__ uint32_t pack2(float lo, float hi) { uint32_t r; asm("cvt.rn.bf16x2.f32 %0, %1, %2;" : "=r"(r) : "f"(hi), "f"(lo)); return r; }
__device__ __forceinline__ uint32_t pack2_relu(float lo, float hi) { uint32_t r; asm("cvt.rn.relu.bf16x2.f32 %0, %1, %2;" : "=r"(r) : "f"(hi), "f"(lo)); return r; }
__device__ __forceinline__ uint32_t hfma2(uint32_t a, uint32_t b, uint32_t c) { uint32_t r; asm("fma.rn.bf16x2 %0, %1, %2, %3;" : "=r"(r) : "r"(a), "r"(b), "r"(c)); return r; }
__device__ __forceinline__ uint32_t hmul2(uint32_t a, uint32_t b) { uint32_t r; asm("mul.rn.bf16x2 %0, %1, %2;" : "=r"(r) : "r"(a), "r"(b)); return r; }
__device__ __forceinline__ float bf_lo(uint32_t v) { return __uint_as_float(v << 16); }
__device__ __forceinline__ float bf_hi(uint32_t v) { return __uint_as_float(v & 0xFFFF0000u); }
__device__ __forceinline__ float bf_round(float v) { return bf_lo(pack2(v, 0.f)); }
__device__ __forceinline__ float ex2(float x) { float r; asm("ex2.approx.ftz.f32 %0, %1;" : "=f"(r) : "f"(x)); return r; }
__device__ __forceinline__ void mma16816(float* d, uint32_t a0, uint32_t a1, uint32_t a2, uint32_t a3, uint32_t b0, uint32_t b1) {
    asm("mma.sync.aligned.m16n8k16.row.col.f32.bf16.bf16.f32 {%0,%1,%2,%3}, {%4,%5,%6,%7}, {%8,%9}, {%0,%1,%2,%3};"
        : "+f"(d[0]), "+f"(d[1]), "+f"(d[2]), "+f"(d[3]) : "r"(a0), "r"(a1), "r"(a2), "r"(a3), "r"(b0), "r"(b1));
}
__device__ __forceinline__ void mma1688(float* d, uint32_t a0, uint32_t a1, uint32_t b0) {
    asm("mma.sync.aligned.m16n8k8.row.col.f32.bf16.bf16.f32 {%0,%1,%2,%3}, {%4,%5}, {%6}, {%0,%1,%2,%3};"
        : "+f"(d[0]), "+f"(d[1]), "+f"(d[2]), "+f"(d[3]) : "r"(a0), "r"(a1), "r"(b0));
}
__device__ __forceinline__ void ldsm4(uint32_t a, uint32_t* r) {
    asm volatile("ldmatrix.sync.aligned.m8n8.x4.shared.b16 {%0,%1,%2,%3}, [%4];" : "=r"(r[0]), "=r"(r[1]), "=r"(r[2]), "=r"(r[3]) : "r"(a));
}
__device__ __forceinline__ void ldsm4t(uint32_t a, uint32_t* r) {
    asm volatile("ldmatrix.sync.aligned.m8n8.x4.trans.shared.b16 {%0,%1,%2,%3}, [%4];" : "=r"(r[0]), "=r"(r[1]), "=r"(r[2]), "=r"(r[3]) : "r"(a));
}
__device__ __forceinline__ uint32_t nz(uint32_t v) { uint32_t r; asm("max.u32 %0, %1, 1;" : "=r"(r) : "r"(v)); return r; }
__device__ __forceinline__ float rcp(float x) { float r; asm("rcp.approx.ftz.f32 %0, %1;" : "=f"(r) : "f"(x)); return r; }
__device__ __forceinline__ uint2 ld_relaxed2(const void* p) { uint2 v; asm volatile("ld.relaxed.gpu.global.v2.u32 {%0,%1}, [%2];" : "=r"(v.x), "=r"(v.y) : "l"(p) : "memory"); return v; }
__host__ __device__ constexpr uint64_t dconst(uint32_t lbo, uint32_t sbo, uint32_t swz) {
    return ((uint64_t)(lbo >> 4) << 16) | ((uint64_t)(sbo >> 4) << 32) | ((uint64_t)swz << 62);
}
__device__ __forceinline__ uint32_t mkdesc(uint32_t addr, uint64_t c) { return (uint32_t)c | ((addr & 0x3FFFF) >> 4); }
#define WG_FENCE() asm volatile("wgmma.fence.sync.aligned;" ::: "memory")
#define WG_COMMIT() asm volatile("wgmma.commit_group.sync.aligned;" ::: "memory")
#define WG_WAIT(n) asm volatile("wgmma.wait_group.sync.aligned %0;" ::"n"(n) : "memory")
template <int N> __device__ __forceinline__ void reg_fence(float* d) {
#pragma unroll
    for (int i = 0; i < N; i++) asm volatile("" : "+f"(d[i])::"memory");
}
template <int N> __device__ __forceinline__ void reg_def(float* d) {
#pragma unroll
    for (int i = 0; i < N; i++) asm volatile("" : "=f"(d[i]));
}
template <int N> __device__ __forceinline__ void reg_def(uint32_t* d) {
#pragma unroll
    for (int i = 0; i < N; i++) asm volatile("" : "=r"(d[i]));
}
__device__ __forceinline__ void wait_flags(const uint32_t* p, uint32_t target, uint32_t mask) {
    int n = 0;
    while (~__ballot_sync(~0u, ld_relaxed(p) == target) & mask) { if (++n > SPIN_LIMIT) __trap(); }
    asm volatile("fence.acquire.gpu;" ::: "memory");
}
__device__ __forceinline__ float silu_bf(uint32_t cbits) {
    const float c = __uint_as_float(cbits << 16);
    return bf_round(__fdividef(c, 1.f + fminf(ex2(-1.4426950408889634f * c), 1e30f)));
}
__device__ __forceinline__ void gemv_part(uint32_t wmbuf, int wp, int lane) {
    const uint32_t wa = wmbuf + wp * 512 + (8 * (lane >> 4) + (lane & 7)) * 32 + ((lane >> 3) & 1) * 16;
    float d[4] = {};
#pragma unroll
    for (int i = 0; i < 4; i++) {
        uint32_t A[4];
        const float2 v = lds2f(wmbuf + 28672 + (wp + 8 * i) * 32 + (lane & 3) * 8);
        ldsm4t(wa + (i < 3 || wp < 4 ? i : 0) * 4096, A);
        mma16816(d, A[0], A[1], A[2], A[3], __float_as_uint(v.x), __float_as_uint(v.y));
    }
    if ((lane & 3) == 0) {
        sts1(wmbuf + 29696 + (wp * 16 + (lane >> 2)) * 4, __float_as_uint(d[0]));
        sts1(wmbuf + 29696 + (wp * 16 + 8 + (lane >> 2)) * 4, __float_as_uint(d[2]));
    }
}
__device__ __forceinline__ uint32_t mod_word(float v, int col, uint32_t target) {
    v = bf_round(v);
    if ((col >= DM && col < 2 * DM) || (col >= 4 * DM && col < 5 * DM)) v += 1.f;
    return (pack2(v, 0.f) << 16) | (target & 0xFFFFu);
}
__device__ __forceinline__ const uint4* mod_src(int i, int r, int j, bool p2) {
    i = min(i, p2 ? 251 : 223);
    return (const uint4*)g_mod + (r & 7) * (6 * DM / 4) + (i < 224 ? (p2 ? 336 : 0) + i : (i < 238 ? 14 * j + i : 14 * j + i + 322));
}
__device__ __forceinline__ void mod_store(uint32_t sb, uint4 v, const uint4* src, int i) {
    const uint32_t tag = lds1(sb + M_EPOCH) + 1;
    while (__any_sync(~0u, (((v.x ^ tag) | (v.y ^ tag) | (v.z ^ tag) | (v.w ^ tag)) & 0xFFFFu) != 0u)) v = ld_relaxed4(src);
    if (i < 224) {
        const int isc = i >= 112, c4 = i - 112 * isc;
        const uint32_t a = sb + M_ST + (c4 >> 2) * 64 + (c4 & 1) * 32 + (c4 & 2) * 4 + (isc ? 0 : 4);
        sts1(a, __byte_perm(v.x, v.y, 0x7632));
        sts1(a + 16, __byte_perm(v.z, v.w, 0x7632));
    } else if (i < 252) {
        sts4(sb + M_G + (i - 224) * 16, make_uint4(v.x & 0xFFFF0000u, v.y & 0xFFFF0000u, v.z & 0xFFFF0000u, v.w & 0xFFFF0000u));
    }
}
__device__ __forceinline__ int pass_f(int fs, int ps) { return 224 * fs + ((fs & 1) ? (ps == 0 ? 96 : ps == 1 ? 32 : 0) : (ps == 0 ? 0 : ps == 1 ? 128 : 192)); }
__device__ __forceinline__ constexpr uint32_t slot_off(int l) { return l * 16384; }
__device__ __forceinline__ constexpr int g1_slot(int s) { return s % 7; }
__device__ __noinline__ void x1_fix(const uint32_t* g, uint32_t sa, int s) {
#pragma unroll 1
    for (int k = 4 * s; k < 4 * s + 4;) {
        const uint4 v = ld_relaxed4((const uint4*)(g + k * 256));
        sts4(sa + k * 1024, v);
        k += 2 * __all_sync(~0u, min(min(v.x, v.y), min(v.z, v.w)) != 0u);
    }
    __syncwarp();
}
struct LnRow { uint32_t nm, hi, lo; };
__device__ __forceinline__ LnRow ln_coeffs(float mean, float msq) {
    const float var = bf_round(fmaxf(msq - mean * mean, 0.f));
    float sd;
    asm("sqrt.approx.f32 %0, %1;" : "=f"(sd) : "f"(bf_round(var + 1e-5f)));
    const float inv = rcp(bf_round(sd)), hi = bf_round(inv);
    LnRow c;
    c.nm = pack2(-bf_round(mean) * hi, -bf_round(mean) * hi);
    c.hi = pack2(hi, hi);
    c.lo = pack2(inv - hi, inv - hi);
    return c;
}
__device__ __forceinline__ uint32_t ln_norm(uint32_t x, const LnRow& c) {
    return hfma2(x, c.hi, c.nm);
}
__device__ __forceinline__ uint32_t ln_mod(uint32_t y, uint32_t sc, uint32_t sh) {
    return hfma2(y, sc, sh);
}

#define LOADW bulk_e(dst, g_wd + (size_t)((f >> 5) * 4 + nq) * 1792, 7168, bar);
template <int sec> __device__ __forceinline__ void ring_loader(const Params& p, uint32_t sb_, int r_, int j_, int lane) {
    const uint32_t sb = opaque(sb_);
    const int r = opaque(r_), j = opaque(j_), nq = j >> 1, fs = 4 * (j & 1) + nq;
    const int fa = pass_f(fs, 0), fb = pass_f(fs, 1), fc = pass_f(fs, 2);
    const uint32_t* h2src = (const uint32_t*)__shfl_sync(~0u, (unsigned long long)(p.actb + (size_t)r * RB_WORDS + RB_H2), 0);
    const CUtensorMap* gmap = (const CUtensorMap*)__shfl_sync(~0u, (unsigned long long)(&p.ga + sec), 0);
#define BAR(i) (sb + M_BAR + 8 * (i))
#define kh (j & 1)
            int sl = 0;
#pragma unroll 1
            for (int s = 0; s < 28; s++) {
                if (s == 7) { wait_flags(g_flag + (8 * r + j) * 192 + 96 + lane, lds1(sb + M_EPOCH) + 1, 0xFFFFu); fence_async_global(); }
                const int ps = s < 14 ? 0 : s < 21 ? 1 : 2;
                const uint32_t half = ps < 2 ? 8192 : 4096;
                const int sp = sl;
                if (s >= 1 && s < 6) mbar_wait(BAR(B_FULL + s - 1), 0);
                mbar_wait(BAR(B_EMPTY + sp), (s >= 7 && s < 14) || s >= 21);
                expect_e(BAR(B_FULL + sp), half);
                tma3_e(sb + slot_off(sp) + sec * half, gmap + 2 * ps, 0, ps ? 64 * sl : 32 * s, ps == 0 ? fa >> 6 : ps == 1 ? fb >> 6 : fc >> 5, BAR(B_FULL + sp));
                sl = sl == 6 ? 0 : sl + 1;
            }
            if (!sec) PROFH(3);
            if (sec) asm volatile("prefetch.tensormap [%0];" ::"l"(&p.om) : "memory");
#pragma unroll 1
            for (int e = 0; e < 4; e++) {
                const uint32_t dst = sb + slot_off(e) + sec * 8192, bar = BAR(B_FULL + e);
                const int f = (e < 2 ? fa + 64 * e : e == 2 ? fb : fc) + 32 * sec;
                mbar_wait(BAR(B_EMPTY + e), 0);
                expect_e(bar, e == 3 && sec ? 0 : 7168);
                if (!(e == 3 && sec)) { LOADW }
            }
            sl = 4;
            int e = 4;
#pragma unroll 1
            for (int grp = 0; grp < 9; grp++) {
                const int ps = grp >= 6 ? 2 : grp >= 3 ? 1 : 0;
                int sidx = grp - 3 * ps;
                if (sec && sidx == 0) { mbar_wait(BAR(B_HRDY + ps), 0); fence_async_global(); }
                sidx += sidx >= nq;
                int f = pass_f(4 * kh + sidx, ps);
#pragma unroll 1
                for (int k = 4 >> ps; k > 0; k--, e++, f += 32) {
                    const uint32_t dst = sb + slot_off(sl), bar = BAR(B_FULL + sl);
                    mbar_wait(BAR(B_EMPTY + sl), e >= 12 && e < 24);
                    if (e >= WIN) mbar_wait(BAR(B_FULL + (sl >= WIN ? sl - WIN : sl + 12 - WIN)), e - WIN >= 12);
                    expect_e(bar, sec ? 8192 : 7168);
                    if (!sec) { LOADW }
                    else bulk_e(dst + 8192, h2src + f * 64, 8192, bar);
                    sl = sl == 11 ? 0 : sl + 1;
                }
            }
            if (!sec) PROFH(4);
}

#define PROF_PARAMS
#define PROF_ARGS
__device__ __noinline__ void helper_late(const Params& p, int r_, int j_, int warp_ PROF_PARAMS) {
    extern __shared__ __align__(1024) unsigned char smem[];
    const uint32_t sb = (uint32_t)__cvta_generic_to_shared(smem);
    const int r = opaque(r_), j = opaque(j_), warp = opaque(warp_), nq = j >> 1, b = 8 * r + j;
    uint32_t* const act = (uint32_t*)__shfl_sync(~0u, (unsigned long long)(p.actb + (size_t)r * RB_WORDS), 0);
    {
        const int lane = fresh_tid() & 31;
        const uint32_t target = lds1(sb + M_EPOCH) + 1;
        if (warp == 8) { expect_e(BAR(B_XCH), 7168); expect_e(BAR(B_XCH + 1), 7168); }
            if (warp == 9) {
#pragma unroll 1
                for (int kv = 0; kv < 2; kv++) {
                    mbar_wait(BAR(B_PUB + kv), 0);
                    wait_flags(g_flag + b * 192 + lane, target, (r >= 2 ? 6u : r == 1 ? 2u : 0u) << (8 * kv));
                    fence_async_global();
                    const uint32_t dst = sb + OFF_Y + (kv ? Y_VR : Y_K);
                    expect_e(BAR(B_KRFULL + kv), r >= 2 ? 28672 : r == 1 ? 14336 : 0);
                    if (r >= 2) bulk_e(dst, act - 2 * RB_WORDS + RB_KV + j * 7168 + kv * 3584, 14336, BAR(B_KRFULL + kv));
                    if (r >= 1) bulk_e(dst + 14336, act - RB_WORDS + RB_KV + j * 7168 + kv * 3584, 14336, BAR(B_KRFULL + kv));
                    if (kv == 0) { PROFH(8); }
                }
            } else if (warp == 8) {
                uint4 v[8];
                mbar_wait(BAR(B_WOFULL), 0);
#pragma unroll
                for (int k = 0; k < 8; k++) v[k] = ld_relaxed4(mod_src(lane + 32 * k, r, j, true));
#pragma unroll
                for (int k = 0; k < 8; k++) mod_store(sb, v[k], mod_src(lane + 32 * k, r, j, true), lane + 32 * k);
                warp_arrive(BAR(B_MOD1));
            } else if (warp == 11) {
                if (kh == 1 && r < 14) {
                    const uint32_t wmbuf = sb + OFF_X + HALF;
                    const int mcol = 2 * DM + 32 * (4 * r + nq);
                    mbar_wait(BAR(B_XFREE), 0);
                    tma3_e(wmbuf, &p.wm2, mcol, 0, 0, BAR(B_WMFULL));
                    tma3_e(wmbuf + 14336, &p.wm2, mcol, 224, 0, BAR(B_WMFULL));
#pragma unroll 1
                    for (int wd = lane; wd < 224; wd += 32) {
                        const uint32_t cb = __ldg((const uint32_t*)p.c + wd);
                        sts1(wmbuf + 28672 + (wd >> 3) * 32 + (wd & 3) * 8 + (wd & 4), pack2(silu_bf(cb & 0xFFFFu), silu_bf(cb >> 16)));
                    }
                    __syncwarp();
                    mbar_wait(BAR(B_WMFULL), 0);
                    const uint32_t wa = wmbuf + (8 * (lane >> 4) + (lane & 7)) * 64 + ((lane >> 3) & 1) * 16;
                    float d[2][4] = {};
#pragma unroll 4
                    for (int ks = 0; ks < 28; ks++) {
                        uint32_t A[8];
                        ldsm4t(wa + ks * 1024, A); ldsm4t(wa + ks * 1024 + 32, A + 4);
                        const float2 v = lds2f(wmbuf + 28672 + ks * 32 + (lane & 3) * 8);
                        mma16816(d[0], A[0], A[1], A[2], A[3], __float_as_uint(v.x), __float_as_uint(v.y));
                        mma16816(d[1], A[4], A[5], A[6], A[7], __float_as_uint(v.x), __float_as_uint(v.y));
                    }
                    const int q = lane & 3, col = mcol + 8 * q + (lane >> 2);
                    const uint32_t word = mod_word(q == 0 ? d[0][0] : q == 1 ? d[0][2] : q == 2 ? d[1][0] : d[1][2], col, target);
#pragma unroll
                    for (int i = 0; i < 8; i++) st_relaxed(g_mod + i * 6 * DM + col, word);
                }
                warp_arrive(BAR(B_WMFREE));
                mbar_wait(BAR(B_VRFULL), 0);
                l2_prefetch_e((const char*)p.wg + (size_t)b * 12544, 12544);
                l2_prefetch_e((const char*)p.wu + (size_t)b * 12544, 12544);
#pragma unroll 1
                for (int k = 0; k < (r < 12 ? 2 : 1); k++) {
                    const int u = 28 * kh + r + 16 * k;
                    expect_e(BAR(B_XFULL + k), 7168);
                    tma3_e(sb + OFF_Y + 102400, &p.dn, 0, 32 * u, 7 * j, BAR(B_XFULL + k));
                    tma3_e(sb + OFF_Y + 102400 + 3584, &p.dn, 0, 32 * u, 7 * (j ^ 1), BAR(B_XFULL + k));
                    mbar_wait(BAR(B_XFULL + k), 1);
                    asm volatile("{\n.reg .pred p;\nelect.sync _|p, 0xffffffff;\n@p cp.async.bulk.global.shared::cta.bulk_group [%0], [%1], 7168;\n"
                                 "cp.async.bulk.commit_group;\ncp.async.bulk.wait_group 0;\n}" ::"l"(g_wd + (size_t)(u * 4 + nq) * 1792), "r"(sb + OFF_Y + 102400) : "memory");
                    __syncwarp();
                }
                warp_arrive(BAR(B_FULLK));
                fence_gpu();
                if (lane < 16) st_relaxed(g_flag + (8 * lane + j) * 192 + 96 + r, target);
            }
        if (warp == 8 || warp == 11) {
            const int sec = warp == 11;
            if (sec) ring_loader<1>(p, sb, r, j, lane); else ring_loader<0>(p, sb, r, j, lane);
            mbar_wait(BAR(B_DONE), 0);
        } else if (warp == 9) {
#pragma unroll
            for (int ev = 0; ev < 4; ev++) { expect_e(BAR(B_GFULL + ev), ev < 2 ? HALF / 2 : 16384); expect_e(BAR(B_XFULL + 2 + ev), ev < 2 ? HALF / 2 : HALF - 16384); }
            mbar_wait(BAR(B_PUB + 2), 0);
            expect_e(BAR(B_FULLV), 4096); expect_e(BAR(B_FULLQ), 4096);
            const int par = (target - 1) & 1;
#pragma unroll 1
            for (int ev = 0; ev < 4; ev++) {
                if (ev == 1) { mbar_wait(BAR(B_FULLK), 1); mbar_wait(BAR(B_PUB + 3), 0); }
                const int tile = (ev & 1) + (ev >> 1) * par * 2;
                const uint32_t dst = sb + (ev == 0 ? OFF_X : OFF_Y + (ev & 1) * HALF), first = ev < 2 ? HALF / 2 : 16384;
                const char* src = (const char*)(act + RB_O + ((ev >> 1) * 2 + tile) * 14336);
                wait_flags(g_flag + b * 192 + (ev < 2 ? 32 : 64 + 32 * ev) + lane, target, ev < 2 ? 0xFFu << (8 * ev) : ~0u);
                fence_async_global();
                if (ev >= 2) bulk_e(sb + OFF_X + X_STAT + (ev & 1) * 49152, act + RB_ST + tile * 1024, 4096, BAR(B_FULLV + (ev & 1)));
                bulk_e(dst, src, first, BAR(B_GFULL + ev));
                bulk_e(dst + first, src + first, HALF - first, BAR(B_XFULL + 2 + ev));
                if (ev) PROFH(4 + ev);
            }
            mbar_wait(BAR(B_XFULL + 5), 1);
#pragma unroll 1
            for (int hf = 0; hf < 2; hf++) {
                const int tile = (par ^ 1) * 2 + hf;
                uint4* xz = (uint4*)(act + RB_X1 + tile * 14336 + j * 1792) + lane;
#pragma unroll
                for (int i = 0; i < 14; i++) xz[i * 32] = make_uint4(0, 0, 0, 0);
                ((uint4*)(act + RB_ST + (tile * 8 + j) * 128))[lane] = make_uint4(0, 0, 0, 0);
            }
#pragma unroll 1
            for (int ps = 0; ps < 3; ps++) {
                mbar_wait(BAR(B_PUB + 6 + ps), 0);
                if (ps == 1) {
                    fence_gpu();
                    if (lane < 8) st_relaxed(g_flag + (8 * r + lane) * 192 + 72 + j, target);
                }
                wait_flags(g_flag + b * 192 + 64 + lane, target, (0x55u << kh) << (8 * ps));
                warp_arrive(BAR(B_HRDY + ps));
                PROFH(9 + ps);
            }
        } else {
#pragma unroll 1
            for (int k = 0; k < 9; k++) {
                if (k == 4 || k == 5 || k == 7) continue;
                uint32_t* fp = k < 2 ? g_flag + (b + 8 * lane) * 192 + k * 8 + lane : g_flag + (8 * r + lane) * 192 + 16 + k * 8 + j;
                mbar_wait(BAR(B_PUB + k), 0);
                fence_gpu();
                if (k < 2 ? (lane == 1 || lane == 2) : lane < 8) st_relaxed(fp, target);
                if (k >= 3 && k <= 5) PROFH(k - 3);
            }
        }
    }
}

__global__ void __cluster_dims__(2, 1, 1) __launch_bounds__(384, 1) fused_block_kernel(const __grid_constant__ Params p) {
    extern __shared__ __align__(1024) unsigned char smem[];
    const uint32_t sb = (uint32_t)__cvta_generic_to_shared(smem);
    const int tid = threadIdx.x, lane = tid & 31, warp = __shfl_sync(~0u, tid >> 5, 0);
    const int m = blockIdx.x >> 1;
    int r, nq;
    if (m < 4) { r = 15; nq = m; }
    else if (m < 36) { r = (m - 4) & 7; nq = (m - 4) >> 3; }
    else { nq = (m - 36) / 7; r = m - 28 - 7 * nq; }
    const int j = opaque(2 * nq + (blockIdx.x & 1)), b = 8 * r + j, fs = 4 * kh + nq;
#define act (p.actb + (size_t)r * RB_WORDS)
    if (lane == 0 && warp < 9 && warp != 6 && warp != 7) {
        const int i0 = warp == 8 ? 0 : 8 + 8 * warp, cnt = warp == 0 || warp == 8 ? 1 : warp < 3 ? 2 : 8;
#pragma unroll
        for (int k = 0; k < 8; k++) if (i0 + k != B_WMFULL) mbar_init(BAR(i0 + k), cnt);
        if (warp == 8) mbar_init(BAR(B_WMFULL), 1);
        asm volatile("fence.mbarrier_init.release.cluster;" ::: "memory");
        fence_async_smem();
    }

    if (warp >= 8) {
        const int lane = fresh_tid() & 31;
        const bool early = kh == 0, gemv = r < 14;
        const int mcol = early ? 16 * (4 * r + nq) : 2 * DM + 32 * (4 * r + nq);
        const uint32_t wmbuf = sb + OFF_Y + HALF;
        if (warp == 8) {
            __syncwarp();
            expect_e(BAR(B_WMFULL), gemv ? 28672 >> early : 0);
            if (early && gemv) { tma3_e(wmbuf, &p.wm, mcol, 0, 0, BAR(B_WMFULL)); tma3_e(wmbuf + 7168, &p.wm, mcol, 224, 0, BAR(B_WMFULL)); }
#pragma unroll
            for (int kb = 0; kb < 7; kb++) {
                expect_e(BAR(B_XFULL + kb), 16384);
                tma3_e(sb + OFF_X + kb * 16384, &p.xm, 64 * kb, 128 * r, 0, BAR(B_XFULL + kb));
            }
        }
        asm volatile("setmaxnreg.dec.sync.aligned.u32 56;");
        if (warp == 9) {
#pragma unroll
            for (int i = 56; i < 64; i++) init_e(BAR(i), 1);
            fence_async_smem();
        }
        bar_arrive(0, 384);
        asm volatile("barrier.cluster.arrive.relaxed.aligned;" ::: "memory");
        if (warp == 8) {
            mbar_wait(BAR(B_XFULL), 0);
            l2_prefetch_e((const char*)p.wqkv + (size_t)b * 9408, 9408);
#pragma unroll 1
            for (int mt = 0; mt < 4; mt++) {
                if (mt == 1) bar_sync(9, 384);
                if (mt == 3) mbar_wait(BAR(B_WMFREE), 0);
                if (mt == 1 && early) mbar_wait(BAR(B_WMFREE), 0);
                if (mt) mbar_wait(BAR(mt == 1 ? B_FULLK : mt == 2 ? B_MOD1 : B_VRFULL), 0);
                const uint32_t bar = BAR(mt == 3 ? B_WOFULL : B_FULLK + mt), dst = sb + (mt < 2 ? OFF_Y : OFF_X) + (mt & 1) * HALF;
                const int c0 = (mt < 2 ? DM + DM * mt : 0) + 56 * j - 8 * kh;
                expect_e(bar, HALF);
                tma3_e(dst, mt == 3 ? &p.wo : &p.qkv, c0, 0, 0, bar);
                tma3_e(dst + HALF / 2, mt == 3 ? &p.wo : &p.qkv, c0, 224, 0, bar);
            }
        } else {
            if (warp == 10 && lane < 13) asm volatile("prefetch.tensormap [%0];" ::"l"(&p.wm + lane) : "memory");
            bar_sync(9, 384);
            if (warp == 11 && early) {
                const uint32_t target = lds1(sb + M_EPOCH) + 1;
                mbar_wait(BAR(B_GEMV), 0);
                float sum = 0.f;
#pragma unroll
                for (int i = 0; i < 8; i++) sum += *(const float*)(smem + OFF_Y + HALF + 29696 + (i * 16 + (lane & 15)) * 4);
                uint32_t* mg = g_mod + mcol + (lane & 15) + (lane >> 4) * 4 * 6 * DM;
                const uint32_t word = mod_word(sum, mcol, target);
                if (gemv) { st_relaxed(mg, word); st_relaxed(mg + 6 * DM, word); st_relaxed(mg + 12 * DM, word); st_relaxed(mg + 18 * DM, word); }
            }
        }
    }
    if (warp < 8) {
        const int w = (warp >> 2) ^ 1, wi = warp & 3;
#define COORDS const int t = fresh_tid() & 127, lane = t & 31, q = lane & 3, lr = lane >> 2, ra = 64 * w + 16 * wi + lr; \
        const uint32_t lx = (lane >> 4) ^ (lane & 7), mrow = (64 * w + 16 * wi + ((lane >> 3) & 1) * 8 + (lane & 7)) * 128; \
        (void)q; (void)lr; (void)ra; (void)lx; (void)mrow;
#define WAIT(i, par) mbar_wait_c(BAR(i), par)
        constexpr uint64_t DB128 = dconst(4096, 1024, 1);
        {
            const int wd = fresh_tid();
            const uint32_t cb = wd < 224 ? __ldg((const uint32_t*)p.c + wd) : 0u;
            if (wd == 255) sts1(sb + M_EPOCH, atomicAdd(&g_ticket, 1u) / NCTA);
            sts1(sb + OFF_Y + HALF + 28672 + (wd >> 3) * 32 + (wd & 3) * 8 + (wd & 4), pack2(silu_bf(cb & 0xFFFFu), silu_bf(cb >> 16)));
        }
        bar_arrive(9, 384);
        bar_sync(0, 384);
        asm volatile("barrier.cluster.arrive.relaxed.aligned;" ::: "memory");
        asm volatile("setmaxnreg.inc.sync.aligned.u32 224;");
        PROFC(0);
        uint32_t xr[16];
        {
            COORDS
            uint32_t h[112];
            LnRow ca, cb;
            const int mi = min(128 * w + t, 223);
            const uint4* msrc = mod_src(mi, r, j, false);
            uint4 mv;
            {
                float ds[4] = {}, da[2][4] = {}, db[2][4] = {};
                const uint32_t ONE2 = 0x3F803F80u;
#pragma unroll
                for (int kb = 0; kb < 7; kb++) {
                    if (kb == 0 && kh == 0) { WAIT(B_WMFULL, 0); gemv_part(sb + OFF_Y + HALF, warp, lane); warp_arrive(BAR(B_GEMV)); }
                    WAIT(B_XFULL + kb, 0);
#pragma unroll
                    for (int k4 = 0; k4 < 4; k4++) ldsm4(sb + OFF_X + mrow + kb * 16384 + (((2 * k4) ^ lx) << 4), h + 16 * kb + 4 * k4);
#pragma unroll
                    for (int k4 = 0; k4 < 4; k4++) {
                        const uint32_t* f = h + 16 * kb + 4 * k4;
                        mma16816(ds, f[0], f[1], f[2], f[3], ONE2, ONE2);
                        mma1688(da[0], f[0], f[1], f[0]); mma1688(db[0], f[0], f[1], f[1]);
                        mma1688(da[1], f[2], f[3], f[2]); mma1688(db[1], f[2], f[3], f[3]);
                    }
                }
#pragma unroll
                for (int i = 0; i < 4; i++) {
                    const int ch = 7 * j + 2 * i + (lane >> 4);
                    ldsm4(sb + OFF_X + mrow + (ch >> 3) * 16384 + (((ch ^ lane) & 7) << 4), xr + 4 * i);
                }
                mv = ld_relaxed4(msrc);
                warp_arrive(BAR(B_XFREE));
                float qa = (lr & 1) ? da[0][1] + da[1][1] : da[0][0] + da[1][0];
                float qb = (lr & 1) ? db[0][3] + db[1][3] : db[0][2] + db[1][2];
                const int src = (lane & ~3) | (lr >> 1);
                qa = __shfl_sync(~0u, qa, src);
                qb = __shfl_sync(~0u, qb, src);
                ca = ln_coeffs(ds[0] * (1.f / DM), qa * (1.f / DM));
                cb = ln_coeffs(ds[2] * (1.f / DM), qb * (1.f / DM));
#pragma unroll
                for (int i = 0; i < 4 * NPRE; i += 2) { h[i] = ln_norm(h[i], ca); h[i + 1] = ln_norm(h[i + 1], cb); }
            }
            PROFC(1);
            {
                float ak[28], av[28], aq[28];
                uint32_t kp[14], vp[14];
                const uint64_t bq0 = (DB128 & ~0xFFFFFFFFull) | (mkdesc(sb + OFF_X, DB128) + kh), bk0 = bq0 + (OFF_Y >> 4), bv0 = bk0 + (HALF >> 4);
                uint32_t* kvg = act + RB_KV + j * 7168 + (8 * w + 2 * wi) * 224 + lane;
                mod_store(sb, mv, msrc, mi);
                bar_sync(3, 256);
                if (warp == 0) warp_arrive(BAR(B_MOD1));
                WAIT(B_FULLK, 0);
                PROFC(2);
                reg_def<28>(ak);
#pragma unroll
                for (int g4 = 0; g4 < 4; g4++) {
#pragma unroll
                    for (int ks = 7 * g4; ks < 7 * g4 + 7; ks++) {
                        const uint4 st = *(const uint4*)(smem + M_ST + ks * 64 + q * 16);
                        if (ks >= NPRE) {
                            h[4 * ks] = ln_norm(h[4 * ks], ca); h[4 * ks + 1] = ln_norm(h[4 * ks + 1], cb);
                            h[4 * ks + 2] = ln_norm(h[4 * ks + 2], ca); h[4 * ks + 3] = ln_norm(h[4 * ks + 3], cb);
                        }
                        h[4 * ks] = ln_mod(h[4 * ks], st.x, st.y); h[4 * ks + 1] = ln_mod(h[4 * ks + 1], st.x, st.y);
                        h[4 * ks + 2] = ln_mod(h[4 * ks + 2], st.z, st.w); h[4 * ks + 3] = ln_mod(h[4 * ks + 3], st.z, st.w);
                    }
                    WG_FENCE();
#pragma unroll
                    for (int ks = 7 * g4; ks < 7 * g4 + 7; ks++) wgmma_rl_56(ak, h[4 * ks], h[4 * ks + 1], h[4 * ks + 2], h[4 * ks + 3], bk0 + ks * 128, ks != 0);
                }
                WG_COMMIT();
                PROFC(3);
                reg_def<28>(av);
                WG_WAIT(0);
                reg_fence<28>(ak);
#pragma unroll
                for (int g = 0; g < 7; g++) {
                    kp[2 * g] = pack2(ak[4 * g], ak[4 * g + 1]); kp[2 * g + 1] = pack2(ak[4 * g + 2], ak[4 * g + 3]);
                    kvg[g * 32] = kp[2 * g]; kvg[224 + g * 32] = kp[2 * g + 1];
                }
                warp_arrive(BAR(B_PUB));
                PROFC(4);
                WAIT(B_FULLV, 0);
                WG_FENCE();
#pragma unroll
                for (int ks = 0; ks < 28; ks++) wgmma_rl_56(av, h[4 * ks], h[4 * ks + 1], h[4 * ks + 2], h[4 * ks + 3], bv0 + ks * 128, ks != 0);
                WG_COMMIT();
                reg_def<28>(aq);
                WAIT(B_FULLQ, 0);
                WG_FENCE();
#pragma unroll
                for (int ks = 0; ks < VPRE; ks++) wgmma_rl_56(aq, h[4 * ks], h[4 * ks + 1], h[4 * ks + 2], h[4 * ks + 3], bq0 + ks * 128, ks != 0);
                WG_COMMIT();
                WG_WAIT(1);
                reg_fence<28>(av);
#pragma unroll
                for (int g = 0; g < 7; g++) {
                    vp[2 * g] = pack2(av[4 * g], av[4 * g + 1]); vp[2 * g + 1] = pack2(av[4 * g + 2], av[4 * g + 3]);
                    kvg[3584 + g * 32] = vp[2 * g]; kvg[3584 + 224 + g * 32] = vp[2 * g + 1];
                }
                warp_arrive(BAR(B_PUB + 1));
                PROFC(5);
                WG_FENCE();
#pragma unroll
                for (int ks = VPRE; ks < 28; ks++) wgmma_rl_56(aq, h[4 * ks], h[4 * ks + 1], h[4 * ks + 2], h[4 * ks + 3], bq0 + ks * 128, ks != 0);
                WG_COMMIT();
                WAIT(B_PUB + 1, 0);
                const uint32_t rg = 8 * w + 2 * wi + ((lane >> 3) & 1);
                const uint32_t ko = sb + OFF_Y + Y_KOWN + rg * 896 + (lane & 7) * 16, qo = sb + OFF_Y + Y_Q + rg * 1024 + (lane >> 4) * 128 + (lane & 7) * 16;
#pragma unroll
                for (int g = 0; g < 6; g += 2) {
                    stsm4(ko + (g + (lane >> 4)) * 128, kp[2 * g], kp[2 * g + 1], kp[2 * g + 2], kp[2 * g + 3]);
                    stsm4(ko + (Y_VOWN - Y_KOWN) + (g + (lane >> 4)) * 128, vp[2 * g], vp[2 * g + 1], vp[2 * g + 2], vp[2 * g + 3]);
                }
                stsm4(ko + (lane >> 4) * (Y_VOWN - Y_KOWN) + 6 * 128, kp[12], kp[13], vp[12], vp[13]);
                WG_WAIT(0);
                reg_fence<28>(aq);
                __syncwarp();
                if (lane < 3 && w == 1) mbar_arrive(BAR(B_EMPTY + lane));
                uint32_t qp[14];
#pragma unroll
                for (int i = 0; i < 14; i++) qp[i] = pack2(aq[2 * i], aq[2 * i + 1]);
                stsm4(qo, qp[0], qp[1], qp[2], qp[3]);
                stsm4(qo + 256, qp[4], qp[5], q < 2 ? qp[6] : 0u, q < 2 ? qp[7] : 0u);
                stsm4(qo + 512, q < 2 ? 0u : qp[6], q < 2 ? 0u : qp[7], qp[8], qp[9]);
                stsm4(qo + 768, qp[10], qp[11], qp[12], qp[13]);
                fence_async_smem();
                if (w == 0) { bar_arrive(4, 256); bar_sync(1, 128); } else { bar_arrive(5, 256); bar_sync(4, 256); }
            }
        }
        PROFC(6);
        WAIT(B_KRFULL, 0);
        PROFC(7);
        {
#pragma unroll 1
            for (int hf = 0; hf < 2; hf++) {
                COORDS
                if (hf > w) bar_sync(5, 256);
                float s[160];
                const float CS = 0.18898223650461361f * 1.4426950408889634f;
                const float NEG = __int_as_float(0xFF800000);
                constexpr uint64_t DQ = dconst(128, 1024, 0), DK = dconst(128, 896, 0);
                {
                    const uint32_t qd = mkdesc(sb + OFF_Y + Y_Q + hf * 8192 + w * 512, DQ), kd = mkdesc(sb + OFF_Y + Y_K + hf * 8 * 896 + w * 384, DK);
                    reg_def<160>(s);
                    WG_FENCE();
                    wgmma_sk_160<DQ, DK>(s, qd, kd, 0);
                    wgmma_sk_160<DQ, DK>(s, qd + 16, kd + 16, 1);
                    wgmma_sk_160<DQ, DK>(s + 80, qd, kd + 20 * 56, 0);
                    wgmma_sk_160<DQ, DK>(s + 80, qd + 16, kd + 20 * 56 + 16, 1);
                    WG_COMMIT();
                    WG_WAIT(0);
                    reg_fence<160>(s);
                }
                if (r < 2) {
                    const int pmin = 4 - 2 * r - hf;
#pragma unroll
                    for (int p4 = 0; p4 < 4; p4++)
                        if (p4 < pmin) {
#pragma unroll
                            for (int i = 0; i < 32; i++) asm volatile("mov.b32 %0, 0xFF800000;" : "=f"(s[32 * p4 + i]));
                        }
                }
                const bool c0 = 2 * q > lr, c1 = 2 * q + 1 > lr;
#pragma unroll
                for (int pp = 0; pp < 4; pp++) {
                    const bool me = pp == wi;
                    float* e = s + 8 * pp;
                    if (me && !c0) { e[0] = NEG; e[6] = NEG; }
                    if (me && !c1) { e[1] = NEG; e[7] = NEG; }
                    if (me) { e[2] = NEG; e[3] = NEG; }
                    e = s + 8 * (pp + 16);
                    if (me && c0) { e[0] = NEG; e[6] = NEG; }
                    if (me && c1) { e[1] = NEG; e[7] = NEG; }
                    if (me) { e[4] = NEG; e[5] = NEG; }
                }
#pragma unroll
                for (int i = 0; i < 24; i++) s[i] = (i >> 3) < wi ? s[136 + i] : s[i];
                int i0 = 0x80000000, i1 = 0x80000000, i2 = 0x80000000, i3 = 0x80000000;
#pragma unroll
                for (int pp = 0; pp < 17; pp++) {
                    const float* e = s + 8 * pp;
                    i0 = __vimax3_s32(i0, __float_as_int(e[0]), __float_as_int(e[1])); i1 = __vimax3_s32(i1, __float_as_int(e[2]), __float_as_int(e[3]));
                    i2 = __vimax3_s32(i2, __float_as_int(e[4]), __float_as_int(e[5])); i3 = __vimax3_s32(i3, __float_as_int(e[6]), __float_as_int(e[7]));
                }
                i0 = max(i0, i2); i1 = max(i1, i3);
                i0 = max(i0, __shfl_xor_sync(~0u, i0, 1)); i1 = max(i1, __shfl_xor_sync(~0u, i1, 1));
                i0 = max(i0, __shfl_xor_sync(~0u, i0, 2)); i1 = max(i1, __shfl_xor_sync(~0u, i1, 2));
                if (__any_sync(~0u, (i0 | i1) < 0)) {
                    uint32_t u0 = ~0u, u1 = ~0u, u2 = ~0u, u3 = ~0u;
#pragma unroll
                    for (int pp = 0; pp < 17; pp++) {
                        const float* e = s + 8 * pp;
                        u0 = __vimin3_u32(u0, __float_as_uint(e[0]), __float_as_uint(e[1])); u1 = __vimin3_u32(u1, __float_as_uint(e[2]), __float_as_uint(e[3]));
                        u2 = __vimin3_u32(u2, __float_as_uint(e[4]), __float_as_uint(e[5])); u3 = __vimin3_u32(u3, __float_as_uint(e[6]), __float_as_uint(e[7]));
                    }
                    u0 = min(u0, u2); u1 = min(u1, u3);
                    u0 = min(u0, __shfl_xor_sync(~0u, u0, 1)); u1 = min(u1, __shfl_xor_sync(~0u, u1, 1));
                    u0 = min(u0, __shfl_xor_sync(~0u, u0, 2)); u1 = min(u1, __shfl_xor_sync(~0u, u1, 2));
                    if (i0 < 0) i0 = u0;
                    if (i1 < 0) i1 = u1;
                }
                const float ma = __int_as_float(i0), mb = __int_as_float(i1);
                const float na = -ma * CS, nb = -mb * CS;
                PROFC(8 + 3 * hf);
                {
                    WAIT(B_VRFULL, 0);
                    float o[16] = {}, rs[4] = {};
                    const uint32_t va = sb + OFF_Y + Y_VR + (8 * hf + ((lane >> 3) & 1)) * 896 + (3 * w + (lane >> 4)) * 128 + (lane & 7) * 16;
                    constexpr uint32_t OWN = Y_VOWN - 32 * 896;
#pragma unroll
                    for (int pp = 0; pp < 17; pp++) {
                        uint32_t B[8];
                        const uint32_t v = va + pp * 1792 + (pp < 3 ? (pp < wi ? 17 * 1792 + OWN : 0) : pp == 16 ? OWN : pp >= 12 ? hf * OWN : 0);
                        ldsm4t(v, B); ldsm4t(v + 256, B + 4);
                        float e[8];
#pragma unroll
                        for (int i = 0; i < 8; i++) e[i] = ex2(fmaf(s[8 * pp + i], CS, (i & 2) ? nb : na));
                        const uint32_t p0 = pack2(e[0], e[1]), p1 = pack2(e[2], e[3]), p2 = pack2(e[4], e[5]), p3 = pack2(e[6], e[7]);
                        mma16816(rs, p0, p1, p2, p3, 0x3F803F80u, 0x3F803F80u);
#pragma unroll
                        for (int g = 0; g < 4; g++) mma16816(o + 4 * g, p0, p1, p2, p3, B[2 * g], B[2 * g + 1]);
                    }
                    PROFC(9 + 3 * hf);
                    const float ia = rcp(rs[0]), ib = rcp(rs[2]);
                    uint32_t* og = act + RB_O + hf * 14336 + (7 * j + 3 * w) * 256 + wi * 64 + lane;
#pragma unroll
                    for (int g = 0; g < 4; g++) {
                        if ((g == 3 - 3 * w) ? ((q >> 1) == w) : true) {
                            og[g * 256] = pack2(o[4 * g] * ia, o[4 * g + 1] * ia);
                            og[g * 256 + 32] = pack2(o[4 * g + 2] * ib, o[4 * g + 3] * ib);
                        }
                    }
                    warp_arrive(BAR(B_PUB + 2 + hf));
                    PROFC(10 + 3 * hf);
                }
            }
        }
        uint32_t x1p[14];
        COORDS
        constexpr uint64_t DT = dconst(1024, 128, 0);
        const uint32_t epoch = lds1(sb + M_EPOCH);
        const int tile = opaque((epoch & 1) * 2 + w);
        {
            float ac[28];
            const uint32_t ad = mkdesc(sb + (w ? OFF_Y + HALF : OFF_X), DT), bd = mkdesc(sb + OFF_X + HALF, DB128) + kh;
            WAIT(B_WOFULL, 0);
            WAIT(B_MOD1, 1);
            WAIT(B_GFULL + w, 0);
            PROFC(28);
            reg_def<28>(ac);
#pragma unroll 1
            for (int u = 0; u < 4; u++) {
                if (u == 2) WAIT(B_XFULL + 2 + w, 1);
                WG_FENCE();
#pragma unroll
                for (int i = 0; i < 7; i++) wgmma_ss_56<DT, DB128>(ac, ad + (7 * u + i) * 128, bd + (7 * u + i) * 128, (u | i) != 0);
            }
            WG_COMMIT();
            WG_WAIT(0);
            reg_fence<28>(ac);
            PROFC(14);
            __syncwarp();
            if (lane < 3) mbar_arrive(BAR(B_EMPTY + 4 - w + lane));
            if (lane < 3 && w == 0) mbar_arrive(BAR(B_EMPTY + lane));
            float ds[4] = {}, da[4] = {}, db[4] = {};
            uint32_t* xo = act + RB_X1 + tile * 14336 + 7 * j * 256 + wi * 64 + lane;
#pragma unroll
            for (int g = 0; g < 7; g++) {
                const float2 ga = *(const float2*)(smem + M_G + (8 * g + 2 * q) * 4);
                x1p[2 * g] = pack2(fmaf(ga.x, ac[4 * g], bf_lo(xr[2 * g])), fmaf(ga.y, ac[4 * g + 1], bf_hi(xr[2 * g])));
                x1p[2 * g + 1] = pack2(fmaf(ga.x, ac[4 * g + 2], bf_lo(xr[2 * g + 1])), fmaf(ga.y, ac[4 * g + 3], bf_hi(xr[2 * g + 1])));
                st_relaxed(xo + g * 256, nz(x1p[2 * g])); st_relaxed(xo + g * 256 + 32, nz(x1p[2 * g + 1]));
                mma1688(ds, x1p[2 * g], x1p[2 * g + 1], 0x3F803F80u);
                mma1688(da, x1p[2 * g], x1p[2 * g + 1], x1p[2 * g]);
                mma1688(db, x1p[2 * g], x1p[2 * g + 1], x1p[2 * g + 1]);
            }
            const int src = (lane & ~3) | (lr >> 1);
            const float qa = __shfl_sync(~0u, (lr & 1) ? da[1] : da[0], src), qb = __shfl_sync(~0u, (lr & 1) ? db[3] : db[2], src);
            const float kk = (q & 1) ? ((q & 2) ? qb : qa) : ((q & 2) ? ds[2] : ds[0]);
            st_relaxed(act + RB_ST + ((tile * 8 + j) * 64 + 16 * wi + lr + 4 * (q & 2)) * 2 + (q & 1), nz(__float_as_uint(kk)));
            if (lane < 8) st_relaxed(g_flag + (8 * r + lane) * 192 + 128 + 32 * w + 4 * j + wi, epoch + 1);
        }
        PROFC(15);
        uint32_t h2a[32], h2b[24];
        {
            const int fa = pass_f(fs, 0), fb = pass_f(fs, 1), fc = pass_f(fs, 2);
            uint32_t* h2g = act + RB_H2 + (8 * w + 2 * wi) * 32 + lane;
            const uint32_t a0 = mkdesc(sb + OFF_Y + w * HALF, DT);
            {
                LnRow ca, cb;
                {
                    const uint32_t* sg = act + RB_ST + ((tile * 8 + 2 * q) * 64 + 16 * wi + lr) * 2;
                    uint2 u[4];
                    WAIT(B_FULLV + w, 1);
                    PROFC(16);
#pragma unroll
                    for (int i = 0; i < 4; i++) { const float2 v = lds2f(sb + OFF_X + X_STAT + w * 49152 + ((2 * q + (i >> 1)) * 64 + 16 * wi + lr + 8 * (i & 1)) * 8); u[i] = make_uint2(__float_as_uint(v.x), __float_as_uint(v.y)); }
                    while (__any_sync(~0u, min(min(min(u[0].x, u[0].y), min(u[1].x, u[1].y)), min(min(u[2].x, u[2].y), min(u[3].x, u[3].y))) == 0u)) {
#pragma unroll
                        for (int i = 0; i < 4; i++) u[i] = ld_relaxed2(sg + (i >> 1) * 128 + (i & 1) * 16);
                    }
                    warp_arrive(BAR(B_EMPTY + 3 + 3 * w));
                    float v[4] = {__uint_as_float(u[0].x) + __uint_as_float(u[2].x), __uint_as_float(u[0].y) + __uint_as_float(u[2].y),
                                  __uint_as_float(u[1].x) + __uint_as_float(u[3].x), __uint_as_float(u[1].y) + __uint_as_float(u[3].y)};
#pragma unroll
                    for (int i = 0; i < 4; i++) { v[i] += __shfl_xor_sync(~0u, v[i], 1); v[i] += __shfl_xor_sync(~0u, v[i], 2); }
                    ca = ln_coeffs(v[0] * (1.f / DM), v[1] * (1.f / DM));
                    cb = ln_coeffs(v[2] * (1.f / DM), v[3] * (1.f / DM));
                }
                const uint32_t ha = sb + OFF_Y + w * HALF + (lane >> 4) * 1024 + (2 * wi + ((lane >> 3) & 1)) * 128 + (lane & 7) * 16;
                const uint32_t sta = sb + M_ST + q * 16;
                const uint32_t* xg = act + RB_X1 + tile * 14336 + (lane >> 4) * 256 + wi * 64 + (lane & 15) * 4;
                uint32_t x[8];
                const uint32_t xs = sb + OFF_Y + w * HALF + (lane >> 4) * 1024 + wi * 256 + (lane & 15) * 16;
                uint4 st[2];
                auto load = [&](int s) {
                    if (s == 4) mbar_wait_c(BAR(B_XFULL + 4 + w), 1);
                    ldsm4(ha + s * 4096, x); ldsm4(ha + s * 4096 + 2048, x + 4);
                    st[0] = lds4(sta + s * 128); st[1] = lds4(sta + s * 128 + 64);
                };
                auto prep = [&](int s, uint32_t* f) {
                    if (__any_sync(~0u, min(min(min(x[0], x[1]), min(x[2], x[3])), min(min(x[4], x[5]), min(x[6], x[7]))) == 0u)) {
                        WG_WAIT(0);
                        x1_fix(xg, xs, s);
                        ldsm4(ha + s * 4096, x); ldsm4(ha + s * 4096 + 2048, x + 4);
                    }
#pragma unroll
                    for (int i = 0; i < 2; i++) {
                        f[4 * i] = ln_mod(ln_norm(x[4 * i], ca), st[i].x, st[i].y); f[4 * i + 1] = ln_mod(ln_norm(x[4 * i + 1], cb), st[i].x, st[i].y);
                        f[4 * i + 2] = ln_mod(ln_norm(x[4 * i + 2], ca), st[i].z, st[i].w); f[4 * i + 3] = ln_mod(ln_norm(x[4 * i + 3], cb), st[i].z, st[i].w);
                    }
                    if (s < 13) load(s + 1);
                    stsm4(ha + s * 4096, f[0], f[1], f[2], f[3]); stsm4(ha + s * 4096 + 2048, f[4], f[5], f[6], f[7]);
                };
                float ac[128];
                uint32_t fr[3][8];
                uint64_t bd = (DB128 & ~0xFFFFFFFFull) | mkdesc(sb, DB128);
                reg_def<128>(ac);
                WAIT(B_GFULL + 2 + w, 0);
                load(0);
                prep(0, fr[0]);
                PROFC(17);
#pragma unroll
                for (int s = 0; s < 14; s++) {
                    const uint32_t* f = fr[s % 3];
                    WAIT(B_FULL + g1_slot(s), s >= 7);
                    WG_FENCE();
                    wgmma_rl_256(ac, f[0], f[1], f[2], f[3], bd, s != 0);
                    wgmma_rl_256(ac, f[4], f[5], f[6], f[7], bd + 128, 1);
                    bd += s == 6 ? p.zero - 6 * 1024ull : 1024;
                    WG_COMMIT();
                    if (s < 13) prep(s + 1, fr[(s + 1) % 3]);
                    if (s > 0) { WG_WAIT(1); warp_arrive(BAR(B_EMPTY + g1_slot(s - 1))); }
                }
                fence_async_smem();
                PROFC(18);
                WG_WAIT(0);
                reg_fence<128>(ac);
                warp_arrive(BAR(B_EMPTY + 6));
#pragma unroll
                for (int g = 0; g < 16; g++) {
                    h2a[2 * g] = hmul2(pack2_relu(ac[4 * g], ac[4 * g + 1]), pack2(ac[64 + 4 * g], ac[64 + 4 * g + 1]));
                    h2a[2 * g + 1] = hmul2(pack2_relu(ac[4 * g + 2], ac[4 * g + 3]), pack2(ac[64 + 4 * g + 2], ac[64 + 4 * g + 3]));
                }
                bar_sync(1 + w, 128);
            }
            PROFC(19);
            {
                float ac[64];
                reg_def<64>(ac);
                const uint32_t bx = mkdesc(sb, dconst(8192, 1024, 1));
#pragma unroll 1
                for (int s = 0; s < 7; s++) {
                    WAIT(B_FULL + s, 0);
                    const uint32_t ad = a0 + s * 512, bd = bx + (slot_off(s) >> 4);
                    WG_FENCE();
#pragma unroll
                    for (int k = 0; k < 4; k++) wgmma_ss_128<DT, DB128>(ac, ad + k * 128, bd + k * 128, (s | k) != 0);
                    WG_COMMIT();
                    if (s == 1) {
#pragma unroll
                        for (int g = 0; g < 16; g++) { h2g[(fa / 8 + g) * 512] = h2a[2 * g]; h2g[(fa / 8 + g) * 512 + 32] = h2a[2 * g + 1]; }
                        warp_arrive(BAR(B_PUB + 6));
                    }
                    if (s > 0) { WG_WAIT(1); warp_arrive(BAR(B_EMPTY + s - 1)); }
                }
                WG_WAIT(0);
                reg_fence<64>(ac);
                warp_arrive(BAR(B_EMPTY + 6));
#pragma unroll
                for (int g = 0; g < 8; g++) {
                    h2b[2 * g] = hmul2(pack2_relu(ac[4 * g], ac[4 * g + 1]), pack2(ac[32 + 4 * g], ac[32 + 4 * g + 1]));
                    h2b[2 * g + 1] = hmul2(pack2_relu(ac[4 * g + 2], ac[4 * g + 3]), pack2(ac[32 + 4 * g + 2], ac[32 + 4 * g + 3]));
                }
            }
            PROFC(27);
            {
                float ac[32];
                reg_def<32>(ac);
                const uint32_t bx = mkdesc(sb, dconst(4096, 512, 2));
#pragma unroll 1
                for (int s = 0; s < 7; s++) {
                    WAIT(B_FULL + s, 1);
                    const uint32_t ad = a0 + s * 512, bd = bx + (slot_off(s) >> 4);
                    WG_FENCE();
#pragma unroll
                    for (int k = 0; k < 4; k++) wgmma_ss_64<DT, dconst(4096, 512, 2)>(ac, ad + k * 128, bd + k * 64, (s | k) != 0);
                    WG_COMMIT();
                    if (s == 1) {
#pragma unroll
                        for (int g = 0; g < 8; g++) { h2g[(fb / 8 + g) * 512] = h2b[2 * g]; h2g[(fb / 8 + g) * 512 + 32] = h2b[2 * g + 1]; }
                        warp_arrive(BAR(B_PUB + 7));
                    }
                    if (s > 0) { WG_WAIT(1); warp_arrive(BAR(B_EMPTY + s - 1)); }
                }
                WG_WAIT(0);
                reg_fence<32>(ac);
                __syncwarp();
                if (lane < 6) mbar_arrive(BAR(B_EMPTY + 6 + lane));
                PROFC(20);
#pragma unroll
                for (int g = 0; g < 4; g++) {
                    h2b[16 + 2 * g] = hmul2(pack2_relu(ac[4 * g], ac[4 * g + 1]), pack2(ac[16 + 4 * g], ac[16 + 4 * g + 1]));
                    h2b[16 + 2 * g + 1] = hmul2(pack2_relu(ac[4 * g + 2], ac[4 * g + 3]), pack2(ac[16 + 4 * g + 2], ac[16 + 4 * g + 3]));
                    h2g[(fc / 8 + g) * 512] = h2b[16 + 2 * g]; h2g[(fc / 8 + g) * 512 + 32] = h2b[16 + 2 * g + 1];
                }
                warp_arrive(BAR(B_PUB + 8));
                asm volatile("barrier.cluster.wait.aligned;" ::: "memory");
                if (lane == 0) {
                    uint32_t rb;
                    asm volatile("mapa.shared::cluster.u32 %0, %1, %2;" : "=r"(rb) : "r"(BAR(B_PEER)), "r"(kh ^ 1));
                    asm volatile("mbarrier.arrive.relaxed.cluster.shared::cluster.b64 _, [%0];" ::"r"(rb) : "memory");
                }
            }
        }
        PROFC(21);
        {
            float ac[56];
            reg_def<56>(ac);
            constexpr uint64_t DAN = dconst(2048, 128, 0);
            constexpr uint64_t DW = dconst(128, 512, 0);
            const uint32_t bx = mkdesc(sb, DW);
#pragma unroll
            for (int e = 0; e < 4; e++) {
                WAIT(B_FULL + e, 0);
                const uint64_t bd = ((DW & ~0xFFFFFFFFull) | bx) + (slot_off(e) >> 4);
                const uint32_t* hh = e < 2 ? h2a + 16 * e : h2b + 16 * (e - 2);
                WG_FENCE();
#pragma unroll
                for (int k = 0; k < (e < 3 ? 4 : 2); k++) wgmma_rl_112(ac, hh[4 * k], hh[4 * k + 1], hh[4 * k + 2], hh[4 * k + 3], bd + (k >> 1) * 512 + (k & 1) * 16, (e | k) != 0);
                WG_COMMIT();
                if (e > 0) { WG_WAIT(1); warp_arrive(BAR(B_EMPTY + e - 1)); }
            }
            PROFC(22);
            uint32_t ad = mkdesc(sb + 4 * 16384 + 8192 + w * 1024, DAN), bd = bx + 4 * 1024, fb_ = BAR(B_FULL + 4), eb_ = BAR(B_EMPTY + 3), par = 0;
#pragma unroll 1
            for (int e = 4; e < 25; e++) {
                mbar_wait_c(fb_, par);
                WG_FENCE();
                wgmma_ss_112<DAN, DW>(ac, ad, bd, 1);
                wgmma_ss_112<DAN, DW>(ac, ad + 256, bd + 16, 1);
                WG_COMMIT();
                WG_WAIT(1);
                warp_arrive(eb_);
                eb_ = fb_ + 8 * (B_EMPTY - B_FULL);
                ad += 1024; bd += 1024; fb_ += 8;
                if (e == 11 || e == 23) { ad -= 12 * 1024; bd -= 12 * 1024; fb_ -= 96; par ^= 1; }
            }
            mbar_wait_cluster(BAR(B_PEER), 0);
            WG_WAIT(0);
            reg_fence<56>(ac);
            PROFC(24);
            uint32_t rdst, rbar;
            asm volatile("mapa.shared::cluster.u32 %0, %1, %2;" : "=r"(rdst) : "r"(sb + OFF_Y + (5 + w) * 16384 + t * 16), "r"(kh ^ 1));
            asm volatile("mapa.shared::cluster.u32 %0, %1, %2;" : "=r"(rbar) : "r"(BAR(B_XCH + w)), "r"(kh ^ 1));
#pragma unroll
            for (int g = 0; g < 3; g++)
                asm volatile("st.async.shared::cluster.mbarrier::complete_tx::bytes.v4.b32 [%0], {%1,%2,%3,%4}, [%5];" ::"r"(rdst + g * 2048),
                             "r"(pack2(ac[28 + 8 * g], ac[29 + 8 * g])), "r"(pack2(ac[30 + 8 * g], ac[31 + 8 * g])), "r"(pack2(ac[32 + 8 * g], ac[33 + 8 * g])),
                             "r"(pack2(ac[34 + 8 * g], ac[35 + 8 * g])), "r"(rbar) : "memory");
            asm volatile("st.async.shared::cluster.mbarrier::complete_tx::bytes.v2.b32 [%0], {%1,%2}, [%3];" ::"r"(rdst + 6144 - t * 8),
                         "r"(pack2(ac[52], ac[53])), "r"(pack2(ac[54], ac[55])), "r"(rbar) : "memory");
            mbar_wait_cluster(BAR(B_XCH + w), 0);
            PROFC(25);
            uint32_t op[14], rv[14];
#pragma unroll
            for (int g = 0; g < 3; g++) *(uint4*)(rv + 4 * g) = *(const uint4*)(smem + OFF_Y + (5 + w) * 16384 + t * 16 + g * 2048);
            *(uint2*)(rv + 12) = *(const uint2*)(smem + OFF_Y + (5 + w) * 16384 + 6144 + t * 8);
#pragma unroll
            for (int i = 0; i < 14; i++) {
                const float2 gb = *(const float2*)(smem + M_G + 224 + (8 * (i >> 1) + 2 * q) * 4);
                op[i] = pack2(fmaf(gb.x, ac[2 * i] + bf_lo(rv[i]), bf_lo(x1p[i])), fmaf(gb.y, ac[2 * i + 1] + bf_hi(rv[i]), bf_hi(x1p[i])));
            }
            WAIT(B_EMPTY + 1, 0);
            const uint32_t oc = sb + OUT_STAGE + warp * 1792;
            const uint32_t oa = oc + (((lane >> 3) & 1) * 8 + (lane & 7)) * 112 + (lane >> 4) * 16;
            stsm4(oa, op[0], op[1], op[2], op[3]); stsm4(oa + 32, op[4], op[5], op[6], op[7]); stsm4(oa + 64, op[8], op[9], op[10], op[11]);
            asm volatile("stmatrix.sync.aligned.m8n8.x2.shared.b16 [%0], {%1,%2};" ::"r"(oa + 96), "r"(op[12]), "r"(op[13]));
            fence_async_smem();
            __syncwarp();
            asm volatile("{\n.reg .pred p;\nelect.sync _|p, 0xffffffff;\n@p cp.async.bulk.tensor.3d.global.shared::cta.bulk_group [%0, {%2, %3, %4}], [%1];\n"
                         "cp.async.bulk.commit_group;\ncp.async.bulk.wait_group.read 0;\n}" ::"l"(&p.om), "r"(oc), "r"(56 * j), "r"(128 * r + 64 * w + 16 * wi), "r"(0) : "memory");
        }
        PROFC(26);
        bar_sync(1 + w, 128);
        if (wi == 0) warp_arrive(BAR(B_DONE));
        return;
    }
    helper_late(p, r, j, warp PROF_ARGS);
}

#undef act
typedef CUresult (*EncodeFn)(CUtensorMap*, CUtensorMapDataType, cuuint32_t, void*, const cuuint64_t*, const cuuint64_t*, const cuuint32_t*,
                             const cuuint32_t*, CUtensorMapInterleave, CUtensorMapSwizzle, CUtensorMapL2promotion, CUtensorMapFloatOOBfill);

static void make_map(EncodeFn fn, CUtensorMap* m, const void* ptr, uint64_t d0, uint64_t d1, uint64_t d2, uint64_t s1, uint64_t s2,
                     uint32_t b0, uint32_t b1, uint32_t b2, CUtensorMapSwizzle sw) {
    cuuint64_t dims[3] = {d0, d1, d2}, strides[2] = {s1, s2};
    cuuint32_t box[3] = {b0, b1, b2}, es[3] = {1, 1, 1};
    CUresult rc = fn(m, CU_TENSOR_MAP_DATA_TYPE_BFLOAT16, 3, (void*)ptr, dims, strides, box, es, CU_TENSOR_MAP_INTERLEAVE_NONE, sw,
                     CU_TENSOR_MAP_L2_PROMOTION_L2_128B, CU_TENSOR_MAP_FLOAT_OOB_FILL_NONE);
    (void)rc;
}

extern "C" void kernel_launch(void* const* d_in, const int* in_sizes, int n_in, void* d_out, int out_size) {
    (void)in_sizes; (void)n_in; (void)out_size;
    static EncodeFn fn = nullptr;
    static uint32_t* act_base = nullptr;
    if (!fn) {
        cudaDriverEntryPointQueryResult st;
        cudaGetDriverEntryPoint("cuTensorMapEncodeTiled", (void**)&fn, cudaEnableDefault, &st);
        void* a = nullptr;
        cudaGetSymbolAddress(&a, g_act);
        act_base = (uint32_t*)(((uintptr_t)a + 0xFFFFF) & ~(uintptr_t)0xFFFFF);
        cudaFuncSetAttribute(fused_block_kernel, cudaFuncAttributeMaxDynamicSharedMemorySize, SMEM_BYTES);
    }
    Params p;
    p.x = (const bf16*)d_in[0];
    const bf16* wqkv = (const bf16*)d_in[1];
    p.wqkv = wqkv;
    p.wop = (const bf16*)d_in[2];
    p.wg = (const bf16*)d_in[4];
    p.wu = (const bf16*)d_in[5];
    p.wd = (const bf16*)d_in[6];
    p.c = (const bf16*)d_in[7];
    p.wmod = (const bf16*)d_in[8];
    p.out = (bf16*)d_out;
    p.zero = 0;
    p.actb = act_base;
    make_map(fn, &p.wm, p.wmod, 2688, 448, 1, 5376, 5376 * 448, 16, 224, 1, CU_TENSOR_MAP_SWIZZLE_NONE);
    make_map(fn, &p.wm2, p.wmod, 2688, 448, 1, 5376, 5376 * 448, 32, 224, 1, CU_TENSOR_MAP_SWIZZLE_NONE);
    make_map(fn, &p.om, p.out, 448, 2048, 1, 896, 896 * 2048, 56, 16, 1, CU_TENSOR_MAP_SWIZZLE_NONE);
    make_map(fn, &p.xm, p.x, 448, 2048, 1, 896, 896 * 2048, 64, 128, 1, CU_TENSOR_MAP_SWIZZLE_128B);
    make_map(fn, &p.qkv, wqkv, 1344, 448, 1, 2688, 2688 * 448, 64, 224, 1, CU_TENSOR_MAP_SWIZZLE_128B);
    make_map(fn, &p.wo, p.wop, 448, 448, 1, 896, 896 * 448, 64, 224, 1, CU_TENSOR_MAP_SWIZZLE_128B);
    make_map(fn, &p.ga, p.wg, 64, 448, 28, 3584, 128, 64, 32, 2, CU_TENSOR_MAP_SWIZZLE_128B);
    make_map(fn, &p.ua, p.wu, 64, 448, 28, 3584, 128, 64, 32, 2, CU_TENSOR_MAP_SWIZZLE_128B);
    make_map(fn, &p.gb, p.wg, 64, 448, 28, 3584, 128, 64, 64, 1, CU_TENSOR_MAP_SWIZZLE_128B);
    make_map(fn, &p.ub, p.wu, 64, 448, 28, 3584, 128, 64, 64, 1, CU_TENSOR_MAP_SWIZZLE_128B);
    make_map(fn, &p.gc, p.wg, 32, 448, 56, 3584, 64, 32, 64, 1, CU_TENSOR_MAP_SWIZZLE_64B);
    make_map(fn, &p.uc, p.wu, 32, 448, 56, 3584, 64, 32, 64, 1, CU_TENSOR_MAP_SWIZZLE_64B);
    make_map(fn, &p.dn, p.wd, 8, 1792, 56, 896, 16, 8, 32, 7, CU_TENSOR_MAP_SWIZZLE_NONE);
    fused_block_kernel<<<NCTA, 384, SMEM_BYTES>>>(p);
}
```

```cpp
#include <cuda_runtime.h>
#include <cuda_bf16.h>
#include <cuda.h>
#include <stdint.h>

typedef __nv_bfloat16 bf16;

template<uint64_t CA, uint64_t CB> __device__ __forceinline__ void wgmma_sk_160(float* d, uint32_t da, uint32_t db, int sd) {
  asm volatile("{\n.reg .pred p;\n.reg .b64 a, b;\nsetp.ne.b32 p, %82, 0;\nmov.b64 a, {%80, %83};\nmov.b64 b, {%81, %84};\n"
    "wgmma.mma_async.sync.aligned.m64n160k16.f32.bf16.bf16 {%0,%1,%2,%3,%4,%5,%6,%7,%8,%9,%10,%11,%12,%13,%14,%15,%16,%17,%18,%19,%20,%21,%22,%23,%24,%25,%26,%27,%28,%29,%30,%31,%32,%33,%34,%35,%36,%37,%38,%39,%40,%41,%42,%43,%44,%45,%46,%47,%48,%49,%50,%51,%52,%53,%54,%55,%56,%57,%58,%59,%60,%61,%62,%63,%64,%65,%66,%67,%68,%69,%70,%71,%72,%73,%74,%75,%76,%77,%78,%79}, a, b, p, 1, 1, 0, 0;\n}\n"
    : "+f"(d[0]),"+f"(d[1]),"+f"(d[2]),"+f"(d[3]),"+f"(d[4]),"+f"(d[5]),"+f"(d[6]),"+f"(d[7]),"+f"(d[8]),"+f"(d[9]),"+f"(d[10]),"+f"(d[11]),"+f"(d[12]),"+f"(d[13]),"+f"(d[14]),"+f"(d[15]),"+f"(d[16]),"+f"(d[17]),"+f"(d[18]),"+f"(d[19]),"+f"(d[20]),"+f"(d[21]),"+f"(d[22]),"+f"(d[23]),"+f"(d[24]),"+f"(d[25]),"+f"(d[26]),"+f"(d[27]),"+f"(d[28]),"+f"(d[29]),"+f"(d[30]),"+f"(d[31]),"+f"(d[32]),"+f"(d[33]),"+f"(d[34]),"+f"(d[35]),"+f"(d[36]),"+f"(d[37]),"+f"(d[38]),"+f"(d[39]),"+f"(d[40]),"+f"(d[41]),"+f"(d[42]),"+f"(d[43]),"+f"(d[44]),"+f"(d[45]),"+f"(d[46]),"+f"(d[47]),"+f"(d[48]),"+f"(d[49]),"+f"(d[50]),"+f"(d[51]),"+f"(d[52]),"+f"(d[53]),"+f"(d[54]),"+f"(d[55]),"+f"(d[56]),"+f"(d[57]),"+f"(d[58]),"+f"(d[59]),"+f"(d[60]),"+f"(d[61]),"+f"(d[62]),"+f"(d[63]),"+f"(d[64]),"+f"(d[65]),"+f"(d[66]),"+f"(d[67]),"+f"(d[68]),"+f"(d[69]),"+f"(d[70]),"+f"(d[71]),"+f"(d[72]),"+f"(d[73]),"+f"(d[74]),"+f"(d[75]),"+f"(d[76]),"+f"(d[77]),"+f"(d[78]),"+f"(d[79])
    : "r"(da), "r"(db), "r"(sd), "n"((uint32_t)(CA >> 32)), "n"((uint32_t)(CB >> 32)));
}
__device__ __forceinline__ void wgmma_rl_56(float* d, uint32_t a0, uint32_t a1, uint32_t a2, uint32_t a3, uint64_t db, int sd) {
  asm volatile("{\n.reg .pred p;\nsetp.ne.b32 p, %33, 0;\n"
    "wgmma.mma_async.sync.aligned.m64n56k16.f32.bf16.bf16 {%0,%1,%2,%3,%4,%5,%6,%7,%8,%9,%10,%11,%12,%13,%14,%15,%16,%17,%18,%19,%20,%21,%22,%23,%24,%25,%26,%27}, {%28,%29,%30,%31}, %32, p, 1, 1, 1;\n}\n"
    : "+f"(d[0]),"+f"(d[1]),"+f"(d[2]),"+f"(d[3]),"+f"(d[4]),"+f"(d[5]),"+f"(d[6]),"+f"(d[7]),"+f"(d[8]),"+f"(d[9]),"+f"(d[10]),"+f"(d[11]),"+f"(d[12]),"+f"(d[13]),"+f"(d[14]),"+f"(d[15]),"+f"(d[16]),"+f"(d[17]),"+f"(d[18]),"+f"(d[19]),"+f"(d[20]),"+f"(d[21]),"+f"(d[22]),"+f"(d[23]),"+f"(d[24]),"+f"(d[25]),"+f"(d[26]),"+f"(d[27])
    : "r"(a0), "r"(a1), "r"(a2), "r"(a3), "l"(db), "r"(sd));
}
template<uint64_t CA, uint64_t CB> __device__ __forceinline__ void wgmma_ss_56(float* d, uint32_t da, uint32_t db, int sd) {
  asm volatile("{\n.reg .pred p;\n.reg .b64 a, b;\nsetp.ne.b32 p, %30, 0;\nmov.b64 a, {%28, %31};\nmov.b64 b, {%29, %32};\n"
    "wgmma.mma_async.sync.aligned.m64n56k16.f32.bf16.bf16 {%0,%1,%2,%3,%4,%5,%6,%7,%8,%9,%10,%11,%12,%13,%14,%15,%16,%17,%18,%19,%20,%21,%22,%23,%24,%25,%26,%27}, a, b, p, 1, 1, 0, 1;\n}\n"
    : "+f"(d[0]),"+f"(d[1]),"+f"(d[2]),"+f"(d[3]),"+f"(d[4]),"+f"(d[5]),"+f"(d[6]),"+f"(d[7]),"+f"(d[8]),"+f"(d[9]),"+f"(d[10]),"+f"(d[11]),"+f"(d[12]),"+f"(d[13]),"+f"(d[14]),"+f"(d[15]),"+f"(d[16]),"+f"(d[17]),"+f"(d[18]),"+f"(d[19]),"+f"(d[20]),"+f"(d[21]),"+f"(d[22]),"+f"(d[23]),"+f"(d[24]),"+f"(d[25]),"+f"(d[26]),"+f"(d[27])
    : "r"(da), "r"(db), "r"(sd), "n"((uint32_t)(CA >> 32)), "n"((uint32_t)(CB >> 32)));
}
__device__ __forceinline__ void wgmma_rl_256(float* d, uint32_t a0, uint32_t a1, uint32_t a2, uint32_t a3, uint64_t db, int sd) {
  asm volatile("{\n.reg .pred p;\nsetp.ne.b32 p, %133, 0;\n"
    "wgmma.mma_async.sync.aligned.m64n256k16.f32.bf16.bf16 {%0,%1,%2,%3,%4,%5,%6,%7,%8,%9,%10,%11,%12,%13,%14,%15,%16,%17,%18,%19,%20,%21,%22,%23,%24,%25,%26,%27,%28,%29,%30,%31,%32,%33,%34,%35,%36,%37,%38,%39,%40,%41,%42,%43,%44,%45,%46,%47,%48,%49,%50,%51,%52,%53,%54,%55,%56,%57,%58,%59,%60,%61,%62,%63,%64,%65,%66,%67,%68,%69,%70,%71,%72,%73,%74,%75,%76,%77,%78,%79,%80,%81,%82,%83,%84,%85,%86,%87,%88,%89,%90,%91,%92,%93,%94,%95,%96,%97,%98,%99,%100,%101,%102,%103,%104,%105,%106,%107,%108,%109,%110,%111,%112,%113,%114,%115,%116,%117,%118,%119,%120,%121,%122,%123,%124,%125,%126,%127}, {%128,%129,%130,%131}, %132, p, 1, 1, 1;\n}\n"
    : "+f"(d[0]),"+f"(d[1]),"+f"(d[2]),"+f"(d[3]),"+f"(d[4]),"+f"(d[5]),"+f"(d[6]),"+f"(d[7]),"+f"(d[8]),"+f"(d[9]),"+f"(d[10]),"+f"(d[11]),"+f"(d[12]),"+f"(d[13]),"+f"(d[14]),"+f"(d[15]),"+f"(d[16]),"+f"(d[17]),"+f"(d[18]),"+f"(d[19]),"+f"(d[20]),"+f"(d[21]),"+f"(d[22]),"+f"(d[23]),"+f"(d[24]),"+f"(d[25]),"+f"(d[26]),"+f"(d[27]),"+f"(d[28]),"+f"(d[29]),"+f"(d[30]),"+f"(d[31]),"+f"(d[32]),"+f"(d[33]),"+f"(d[34]),"+f"(d[35]),"+f"(d[36]),"+f"(d[37]),"+f"(d[38]),"+f"(d[39]),"+f"(d[40]),"+f"(d[41]),"+f"(d[42]),"+f"(d[43]),"+f"(d[44]),"+f"(d[45]),"+f"(d[46]),"+f"(d[47]),"+f"(d[48]),"+f"(d[49]),"+f"(d[50]),"+f"(d[51]),"+f"(d[52]),"+f"(d[53]),"+f"(d[54]),"+f"(d[55]),"+f"(d[56]),"+f"(d[57]),"+f"(d[58]),"+f"(d[59]),"+f"(d[60]),"+f"(d[61]),"+f"(d[62]),"+f"(d[63]),"+f"(d[64]),"+f"(d[65]),"+f"(d[66]),"+f"(d[67]),"+f"(d[68]),"+f"(d[69]),"+f"(d[70]),"+f"(d[71]),"+f"(d[72]),"+f"(d[73]),"+f"(d[74]),"+f"(d[75]),"+f"(d[76]),"+f"(d[77]),"+f"(d[78]),"+f"(d[79]),"+f"(d[80]),"+f"(d[81]),"+f"(d[82]),"+f"(d[83]),"+f"(d[84]),"+f"(d[85]),"+f"(d[86]),"+f"(d[87]),"+f"(d[88]),"+f"(d[89]),"+f"(d[90]),"+f"(d[91]),"+f"(d[92]),"+f"(d[93]),"+f"(d[94]),"+f"(d[95]),"+f"(d[96]),"+f"(d[97]),"+f"(d[98]),"+f"(d[99]),"+f"(d[100]),"+f"(d[101]),"+f"(d[102]),"+f"(d[103]),"+f"(d[104]),"+f"(d[105]),"+f"(d[106]),"+f"(d[107]),"+f"(d[108]),"+f"(d[109]),"+f"(d[110]),"+f"(d[111]),"+f"(d[112]),"+f"(d[113]),"+f"(d[114]),"+f"(d[115]),"+f"(d[116]),"+f"(d[117]),"+f"(d[118]),"+f"(d[119]),"+f"(d[120]),"+f"(d[121]),"+f"(d[122]),"+f"(d[123]),"+f"(d[124]),"+f"(d[125]),"+f"(d[126]),"+f"(d[127])
    : "r"(a0), "r"(a1), "r"(a2), "r"(a3), "l"(db), "r"(sd));
}
template<uint64_t CA, uint64_t CB> __device__ __forceinline__ void wgmma_ss_128(float* d, uint32_t da, uint32_t db, int sd) {
  asm volatile("{\n.reg .pred p;\n.reg .b64 a, b;\nsetp.ne.b32 p, %66, 0;\nmov.b64 a, {%64, %67};\nmov.b64 b, {%65, %68};\n"
    "wgmma.mma_async.sync.aligned.m64n128k16.f32.bf16.bf16 {%0,%1,%2,%3,%4,%5,%6,%7,%8,%9,%10,%11,%12,%13,%14,%15,%16,%17,%18,%19,%20,%21,%22,%23,%24,%25,%26,%27,%28,%29,%30,%31,%32,%33,%34,%35,%36,%37,%38,%39,%40,%41,%42,%43,%44,%45,%46,%47,%48,%49,%50,%51,%52,%53,%54,%55,%56,%57,%58,%59,%60,%61,%62,%63}, a, b, p, 1, 1, 0, 1;\n}\n"
    : "+f"(d[0]),"+f"(d[1]),"+f"(d[2]),"+f"(d[3]),"+f"(d[4]),"+f"(d[5]),"+f"(d[6]),"+f"(d[7]),"+f"(d[8]),"+f"(d[9]),"+f"(d[10]),"+f"(d[11]),"+f"(d[12]),"+f"(d[13]),"+f"(d[14]),"+f"(d[15]),"+f"(d[16]),"+f"(d[17]),"+f"(d[18]),"+f"(d[19]),"+f"(d[20]),"+f"(d[21]),"+f"(d[22]),"+f"(d[23]),"+f"(d[24]),"+f"(d[25]),"+f"(d[26]),"+f"(d[27]),"+f"(d[28]),"+f"(d[29]),"+f"(d[30]),"+f"(d[31]),"+f"(d[32]),"+f"(d[33]),"+f"(d[34]),"+f"(d[35]),"+f"(d[36]),"+f"(d[37]),"+f"(d[38]),"+f"(d[39]),"+f"(d[40]),"+f"(d[41]),"+f"(d[42]),"+f"(d[43]),"+f"(d[44]),"+f"(d[45]),"+f"(d[46]),"+f"(d[47]),"+f"(d[48]),"+f"(d[49]),"+f"(d[50]),"+f"(d[51]),"+f"(d[52]),"+f"(d[53]),"+f"(d[54]),"+f"(d[55]),"+f"(d[56]),"+f"(d[57]),"+f"(d[58]),"+f"(d[59]),"+f"(d[60]),"+f"(d[61]),"+f"(d[62]),"+f"(d[63])
    : "r"(da), "r"(db), "r"(sd), "n"((uint32_t)(CA >> 32)), "n"((uint32_t)(CB >> 32)));
}
template<uint64_t CA, uint64_t CB> __device__ __forceinline__ void wgmma_ss_64(float* d, uint32_t da, uint32_t db, int sd) {
  asm volatile("{\n.reg .pred p;\n.reg .b64 a, b;\nsetp.ne.b32 p, %34, 0;\nmov.b64 a, {%32, %35};\nmov.b64 b, {%33, %36};\n"
    "wgmma.mma_async.sync.aligned.m64n64k16.f32.bf16.bf16 {%0,%1,%2,%3,%4,%5,%6,%7,%8,%9,%10,%11,%12,%13,%14,%15,%16,%17,%18,%19,%20,%21,%22,%23,%24,%25,%26,%27,%28,%29,%30,%31}, a, b, p, 1, 1, 0, 1;\n}\n"
    : "+f"(d[0]),"+f"(d[1]),"+f"(d[2]),"+f"(d[3]),"+f"(d[4]),"+f"(d[5]),"+f"(d[6]),"+f"(d[7]),"+f"(d[8]),"+f"(d[9]),"+f"(d[10]),"+f"(d[11]),"+f"(d[12]),"+f"(d[13]),"+f"(d[14]),"+f"(d[15]),"+f"(d[16]),"+f"(d[17]),"+f"(d[18]),"+f"(d[19]),"+f"(d[20]),"+f"(d[21]),"+f"(d[22]),"+f"(d[23]),"+f"(d[24]),"+f"(d[25]),"+f"(d[26]),"+f"(d[27]),"+f"(d[28]),"+f"(d[29]),"+f"(d[30]),"+f"(d[31])
    : "r"(da), "r"(db), "r"(sd), "n"((uint32_t)(CA >> 32)), "n"((uint32_t)(CB >> 32)));
}
template<uint64_t CA, uint64_t CB> __device__ __forceinline__ void wgmma_ss_112(float* d, uint32_t da, uint32_t db, int sd) {
  asm volatile("{\n.reg .pred p;\n.reg .b64 a, b;\nsetp.ne.b32 p, %58, 0;\nmov.b64 a, {%56, %59};\nmov.b64 b, {%57, %60};\n"
    "wgmma.mma_async.sync.aligned.m64n112k16.f32.bf16.bf16 {%0,%1,%2,%3,%4,%5,%6,%7,%8,%9,%10,%11,%12,%13,%14,%15,%16,%17,%18,%19,%20,%21,%22,%23,%24,%25,%26,%27,%28,%29,%30,%31,%32,%33,%34,%35,%36,%37,%38,%39,%40,%41,%42,%43,%44,%45,%46,%47,%48,%49,%50,%51,%52,%53,%54,%55}, a, b, p, 1, 1, 0, 1;\n}\n"
    : "+f"(d[0]),"+f"(d[1]),"+f"(d[2]),"+f"(d[3]),"+f"(d[4]),"+f"(d[5]),"+f"(d[6]),"+f"(d[7]),"+f"(d[8]),"+f"(d[9]),"+f"(d[10]),"+f"(d[11]),"+f"(d[12]),"+f"(d[13]),"+f"(d[14]),"+f"(d[15]),"+f"(d[16]),"+f"(d[17]),"+f"(d[18]),"+f"(d[19]),"+f"(d[20]),"+f"(d[21]),"+f"(d[22]),"+f"(d[23]),"+f"(d[24]),"+f"(d[25]),"+f"(d[26]),"+f"(d[27]),"+f"(d[28]),"+f"(d[29]),"+f"(d[30]),"+f"(d[31]),"+f"(d[32]),"+f"(d[33]),"+f"(d[34]),"+f"(d[35]),"+f"(d[36]),"+f"(d[37]),"+f"(d[38]),"+f"(d[39]),"+f"(d[40]),"+f"(d[41]),"+f"(d[42]),"+f"(d[43]),"+f"(d[44]),"+f"(d[45]),"+f"(d[46]),"+f"(d[47]),"+f"(d[48]),"+f"(d[49]),"+f"(d[50]),"+f"(d[51]),"+f"(d[52]),"+f"(d[53]),"+f"(d[54]),"+f"(d[55])
    : "r"(da), "r"(db), "r"(sd), "n"((uint32_t)(CA >> 32)), "n"((uint32_t)(CB >> 32)));
}
__device__ __forceinline__ void wgmma_rl_112(float* d, uint32_t a0, uint32_t a1, uint32_t a2, uint32_t a3, uint64_t db, int sd) {
  asm volatile("{\n.reg .pred p;\nsetp.ne.b32 p, %61, 0;\n"
    "wgmma.mma_async.sync.aligned.m64n112k16.f32.bf16.bf16 {%0,%1,%2,%3,%4,%5,%6,%7,%8,%9,%10,%11,%12,%13,%14,%15,%16,%17,%18,%19,%20,%21,%22,%23,%24,%25,%26,%27,%28,%29,%30,%31,%32,%33,%34,%35,%36,%37,%38,%39,%40,%41,%42,%43,%44,%45,%46,%47,%48,%49,%50,%51,%52,%53,%54,%55}, {%56,%57,%58,%59}, %60, p, 1, 1, 1;\n}\n"
    : "+f"(d[0]),"+f"(d[1]),"+f"(d[2]),"+f"(d[3]),"+f"(d[4]),"+f"(d[5]),"+f"(d[6]),"+f"(d[7]),"+f"(d[8]),"+f"(d[9]),"+f"(d[10]),"+f"(d[11]),"+f"(d[12]),"+f"(d[13]),"+f"(d[14]),"+f"(d[15]),"+f"(d[16]),"+f"(d[17]),"+f"(d[18]),"+f"(d[19]),"+f"(d[20]),"+f"(d[21]),"+f"(d[22]),"+f"(d[23]),"+f"(d[24]),"+f"(d[25]),"+f"(d[26]),"+f"(d[27]),"+f"(d[28]),"+f"(d[29]),"+f"(d[30]),"+f"(d[31]),"+f"(d[32]),"+f"(d[33]),"+f"(d[34]),"+f"(d[35]),"+f"(d[36]),"+f"(d[37]),"+f"(d[38]),"+f"(d[39]),"+f"(d[40]),"+f"(d[41]),"+f"(d[42]),"+f"(d[43]),"+f"(d[44]),"+f"(d[45]),"+f"(d[46]),"+f"(d[47]),"+f"(d[48]),"+f"(d[49]),"+f"(d[50]),"+f"(d[51]),"+f"(d[52]),"+f"(d[53]),"+f"(d[54]),"+f"(d[55])
    : "r"(a0), "r"(a1), "r"(a2), "r"(a3), "l"(db), "r"(sd));
}

constexpr int DM = 448;
constexpr int NCTA = 128;
#define WIN 5
#define NPRE 14
#define VPRE 3
constexpr int SPIN_LIMIT = 1 << 22;

constexpr uint32_t OFF_X = 0, OFF_Y = 114688, OFF_MISC = 229376, SMEM_BYTES = 232448;
constexpr uint32_t Y_VR = 0, Y_K = 28672, Y_KOWN = 57344, Y_VOWN = 71680, Y_Q = 86016;
constexpr uint32_t HALF = 57344;
constexpr uint32_t X_STAT = 49152;
constexpr uint32_t OUT_STAGE = 4 * 16384;
constexpr uint32_t M_BAR = OFF_MISC;
constexpr uint32_t M_ST = OFF_MISC + 512;
constexpr uint32_t M_G = OFF_MISC + 2304;
constexpr uint32_t M_EPOCH = OFF_MISC + 3040;
enum { B_XFULL = 0, B_FULLK = 7, B_FULLV = 8, B_FULLQ, B_KRFULL, B_VRFULL, B_WOFULL, B_XCH, B_MOD1 = 15, B_FULL = 16, B_WMFULL = 30,
       B_EMPTY = 32, B_PEER = 45, B_DUMMY,
       B_PUB = 47,
       B_XFREE = B_PUB + 4, B_GEMV,
       B_WMFREE = 56, B_HRDY, B_GFULL = B_HRDY + 3, B_DONE = 31 };

__device__ uint32_t g_ticket;
__device__ __align__(128) uint32_t g_mod[8 * 6 * DM];
__device__ __align__(128) uint32_t g_flag[144 * 192];
constexpr int RB_WORDS = 262144, RB_KV = 0, RB_O = 57344, RB_X1 = 86016, RB_H2 = 143360, RB_ST = 258048;
__device__ __align__(128) uint32_t g_act[17 * RB_WORDS];
__device__ __align__(128) uint32_t g_wd[56 * 4 * 1792];
#define PROFH(id)
#define PROFH1(id)
#define PROFC(id)

struct alignas(64) Params {
    CUtensorMap wm, wm2, om, xm, qkv, wo, ga, ua, gb, ub, gc, uc, dn;
    const bf16 *x, *c, *wqkv, *wmod, *wg, *wu, *wd, *wop;
    bf16* out;
    uint32_t* actb;
    uint32_t zero;
};

__device__ __forceinline__ void mbar_init(uint32_t bar, int cnt) { asm volatile("mbarrier.init.shared::cta.b64 [%0], %1;" ::"r"(bar), "r"(cnt) : "memory"); }
__device__ __forceinline__ void mbar_arrive(uint32_t bar) { asm volatile("mbarrier.arrive.shared::cta.b64 _, [%0];" ::"r"(bar) : "memory"); }
__device__ __forceinline__ void mbar_wait(uint32_t bar, uint32_t parity) {
    uint32_t ok; int n = 0;
    do {
        asm volatile("{\n.reg .pred p;\nmbarrier.try_wait.parity.shared::cta.b64 p, [%1], %2;\nselp.u32 %0, 1, 0, p;\n}" : "=r"(ok) : "r"(bar), "r"(parity) : "memory");
        if (++n > SPIN_LIMIT) __trap();
    } while (!ok);
}
__device__ __forceinline__ void mbar_wait_c(uint32_t bar, uint32_t parity) {
    asm volatile("{\n.reg .pred p;\nWL:\nmbarrier.try_wait.parity.shared::cta.b64 p, [%0], %1, 0x989680;\n@!p bra WL;\n}" ::"r"(bar), "r"(parity) : "memory");
}
__device__ __forceinline__ void mbar_wait_cluster(uint32_t bar, uint32_t parity) {
    asm volatile("{\n.reg .pred p;\nWL:\nmbarrier.try_wait.parity.acquire.cluster.shared::cta.b64 p, [%0], %1, 0x989680;\n@!p bra WL;\n}" ::"r"(bar), "r"(parity) : "memory");
}
__device__ __forceinline__ void warp_arrive(uint32_t bar) {
    __syncwarp();
    asm volatile("{\n.reg .pred p;\nelect.sync _|p, 0xffffffff;\n@p mbarrier.arrive.shared::cta.b64 _, [%0];\n}" ::"r"(bar) : "memory");
}
__device__ __forceinline__ int opaque(int v) { return __shfl_sync(~0u, v, 0); }
__device__ __forceinline__ int fresh_tid() { int v; asm volatile("mov.u32 %0, %%tid.x;" : "=r"(v)); return v; }
__device__ __forceinline__ void bar_sync(int id, int n) { asm volatile("bar.sync %0, %1;" ::"r"(id), "r"(n) : "memory"); }
__device__ __forceinline__ void bar_arrive(int id, int n) { asm volatile("bar.arrive %0, %1;" ::"r"(id), "r"(n) : "memory"); }
__device__ __forceinline__ void fence_async_smem() { asm volatile("fence.proxy.async.shared::cta;" ::: "memory"); }
__device__ __forceinline__ void fence_async_global() { asm volatile("fence.proxy.async.global;" ::: "memory"); }
__device__ __forceinline__ void fence_gpu() { asm volatile("fence.release.gpu;" ::: "memory"); }
__device__ __forceinline__ void expect_e(uint32_t bar, uint32_t bytes) {
    asm volatile("{\n.reg .pred p;\nelect.sync _|p, 0xffffffff;\n@p mbarrier.arrive.expect_tx.shared::cta.b64 _, [%0], %1;\n}" ::"r"(bar), "r"(bytes) : "memory");
}
__device__ __forceinline__ void tma3_e(uint32_t dst, const CUtensorMap* m, int c0, int c1, int c2, uint32_t bar) {
    asm volatile("{\n.reg .pred p;\nelect.sync _|p, 0xffffffff;\n@p cp.async.bulk.tensor.3d.shared::cluster.global.mbarrier::complete_tx::bytes [%0], [%1, {%3, %4, %5}], [%2];\n}"
                 ::"r"(dst), "l"(m), "r"(bar), "r"(c0), "r"(c1), "r"(c2) : "memory");
}
__device__ __forceinline__ void bulk_e(uint32_t dst, const void* src, uint32_t bytes, uint32_t bar) {
    asm volatile("{\n.reg .pred p;\nelect.sync _|p, 0xffffffff;\n@p cp.async.bulk.shared::cluster.global.mbarrier::complete_tx::bytes [%0], [%1], %2, [%3];\n}"
                 ::"r"(dst), "l"(src), "r"(bytes), "r"(bar) : "memory");
}
__device__ __forceinline__ void init_e(uint32_t bar, int cnt) {
    asm volatile("{\n.reg .pred p;\nelect.sync _|p, 0xffffffff;\n@p mbarrier.init.shared::cta.b64 [%0], %1;\n}" ::"r"(bar), "r"(cnt) : "memory");
}
__device__ __forceinline__ void l2_prefetch_e(const void* src, uint32_t bytes) {
    asm volatile("{\n.reg .pred p;\nelect.sync _|p, 0xffffffff;\n@p cp.async.bulk.prefetch.L2.global [%0], %1;\n}" ::"l"(src), "r"(bytes) : "memory");
}
__device__ __forceinline__ uint32_t ld_relaxed(const uint32_t* p) { uint32_t v; asm volatile("ld.relaxed.gpu.global.u32 %0, [%1];" : "=r"(v) : "l"(p) : "memory"); return v; }
__device__ __forceinline__ void st_relaxed(uint32_t* p, uint32_t v) { asm volatile("st.relaxed.gpu.global.u32 [%0], %1;" ::"l"(p), "r"(v) : "memory"); }
__device__ __forceinline__ uint4 ld_relaxed4(const uint4* p) { uint4 v; asm volatile("ld.relaxed.gpu.global.v4.u32 {%0,%1,%2,%3}, [%4];" : "=r"(v.x), "=r"(v.y), "=r"(v.z), "=r"(v.w) : "l"(p) : "memory"); return v; }
__device__ __forceinline__ uint4 lds4(uint32_t a) { uint4 v; asm volatile("ld.shared.v4.u32 {%0,%1,%2,%3}, [%4];" : "=r"(v.x), "=r"(v.y), "=r"(v.z), "=r"(v.w) : "r"(a) : "memory"); return v; }
__device__ __forceinline__ float2 lds2f(uint32_t a) { float2 v; asm volatile("ld.shared.v2.f32 {%0,%1}, [%2];" : "=f"(v.x), "=f"(v.y) : "r"(a) : "memory"); return v; }
__device__ __forceinline__ uint32_t lds1(uint32_t a) { uint32_t v; asm volatile("ld.shared.u32 %0, [%1];" : "=r"(v) : "r"(a) : "memory"); return v; }
__device__ __forceinline__ void sts4(uint32_t a, uint4 v) { asm volatile("st.shared.v4.u32 [%0], {%1,%2,%3,%4};" ::"r"(a), "r"(v.x), "r"(v.y), "r"(v.z), "r"(v.w) : "memory"); }
__device__ __forceinline__ void sts1(uint32_t a, uint32_t v) { asm volatile("st.shared.u32 [%0], %1;" ::"r"(a), "r"(v) : "memory"); }
__device__ __forceinline__ void stsm4(uint32_t a, uint32_t r0, uint32_t r1, uint32_t r2, uint32_t r3) {
    asm volatile("stmatrix.sync.aligned.m8n8.x4.shared.b16 [%0], {%1,%2,%3,%4};" ::"r"(a), "r"(r0), "r"(r1), "r"(r2), "r"(r3));
}
__device__ __forceinline__ uint32_t pack2(float lo, float hi) { uint32_t r; asm("cvt.rn.bf16x2.f32 %0, %1, %2;" : "=r"(r) : "f"(hi), "f"(lo)); return r; }
__device__ __forceinline__ uint32_t pack2_relu(float lo, float hi) { uint32_t r; asm("cvt.rn.relu.bf16x2.f32 %0, %1, %2;" : "=r"(r) : "f"(hi), "f"(lo)); return r; }
__device__ __forceinline__ uint32_t hfma2(uint32_t a, uint32_t b, uint32_t c) { uint32_t r; asm("fma.rn.bf16x2 %0, %1, %2, %3;" : "=r"(r) : "r"(a), "r"(b), "r"(c)); return r; }
__device__ __forceinline__ uint32_t hmul2(uint32_t a, uint32_t b) { uint32_t r; asm("mul.rn.bf16x2 %0, %1, %2;" : "=r"(r) : "r"(a), "r"(b)); return r; }
__device__ __forceinline__ float bf_lo(uint32_t v) { return __uint_as_float(v << 16); }
__device__ __forceinline__ float bf_hi(uint32_t v) { return __uint_as_float(v & 0xFFFF0000u); }
__device__ __forceinline__ float bf_round(float v) { return bf_lo(pack2(v, 0.f)); }
__device__ __forceinline__ float ex2(float x) { float r; asm("ex2.approx.ftz.f32 %0, %1;" : "=f"(r) : "f"(x)); return r; }
__device__ __forceinline__ void mma16816(float* d, uint32_t a0, uint32_t a1, uint32_t a2, uint32_t a3, uint32_t b0, uint32_t b1) {
    asm("mma.sync.aligned.m16n8k16.row.col.f32.bf16.bf16.f32 {%0,%1,%2,%3}, {%4,%5,%6,%7}, {%8,%9}, {%0,%1,%2,%3};"
        : "+f"(d[0]), "+f"(d[1]), "+f"(d[2]), "+f"(d[3]) : "r"(a0), "r"(a1), "r"(a2), "r"(a3), "r"(b0), "r"(b1));
}
__device__ __forceinline__ void mma1688(float* d, uint32_t a0, uint32_t a1, uint32_t b0) {
    asm("mma.sync.aligned.m16n8k8.row.col.f32.bf16.bf16.f32 {%0,%1,%2,%3}, {%4,%5}, {%6}, {%0,%1,%2,%3};"
        : "+f"(d[0]), "+f"(d[1]), "+f"(d[2]), "+f"(d[3]) : "r"(a0), "r"(a1), "r"(b0));
}
__device__ __forceinline__ void ldsm4(uint32_t a, uint32_t* r) {
    asm volatile("ldmatrix.sync.aligned.m8n8.x4.shared.b16 {%0,%1,%2,%3}, [%4];" : "=r"(r[0]), "=r"(r[1]), "=r"(r[2]), "=r"(r[3]) : "r"(a));
}
__device__ __forceinline__ void ldsm4t(uint32_t a, uint32_t* r) {
    asm volatile("ldmatrix.sync.aligned.m8n8.x4.trans.shared.b16 {%0,%1,%2,%3}, [%4];" : "=r"(r[0]), "=r"(r[1]), "=r"(r[2]), "=r"(r[3]) : "r"(a));
}
__device__ __forceinline__ uint32_t nz(uint32_t v) { uint32_t r; asm("max.u32 %0, %1, 1;" : "=r"(r) : "r"(v)); return r; }
__device__ __forceinline__ float rcp(float x) { float r; asm("rcp.approx.ftz.f32 %0, %1;" : "=f"(r) : "f"(x)); return r; }
__device__ __forceinline__ uint2 ld_relaxed2(const void* p) { uint2 v; asm volatile("ld.relaxed.gpu.global.v2.u32 {%0,%1}, [%2];" : "=r"(v.x), "=r"(v.y) : "l"(p) : "memory"); return v; }
__host__ __device__ constexpr uint64_t dconst(uint32_t lbo, uint32_t sbo, uint32_t swz) {
    return ((uint64_t)(lbo >> 4) << 16) | ((uint64_t)(sbo >> 4) << 32) | ((uint64_t)swz << 62);
}
__device__ __forceinline__ uint32_t mkdesc(uint32_t addr, uint64_t c) { return (uint32_t)c | ((addr & 0x3FFFF) >> 4); }
#define WG_FENCE() asm volatile("wgmma.fence.sync.aligned;" ::: "memory")
#define WG_COMMIT() asm volatile("wgmma.commit_group.sync.aligned;" ::: "memory")
#define WG_WAIT(n) asm volatile("wgmma.wait_group.sync.aligned %0;" ::"n"(n) : "memory")
template <int N> __device__ __forceinline__ void reg_fence(float* d) {
#pragma unroll
    for (int i = 0; i < N; i++) asm volatile("" : "+f"(d[i])::"memory");
}
template <int N> __device__ __forceinline__ void reg_def(float* d) {
#pragma unroll
    for (int i = 0; i < N; i++) asm volatile("" : "=f"(d[i]));
}
template <int N> __device__ __forceinline__ void reg_def(uint32_t* d) {
#pragma unroll
    for (int i = 0; i < N; i++) asm volatile("" : "=r"(d[i]));
}
__device__ __forceinline__ void wait_flags(const uint32_t* p, uint32_t target, uint32_t mask) {
    int n = 0;
    while (~__ballot_sync(~0u, ld_relaxed(p) == target) & mask) { if (++n > SPIN_LIMIT) __trap(); }
    asm volatile("fence.acquire.gpu;" ::: "memory");
}
__device__ __forceinline__ float silu_bf(uint32_t cbits) {
    const float c = __uint_as_float(cbits << 16);
    return bf_round(__fdividef(c, 1.f + fminf(ex2(-1.4426950408889634f * c), 1e30f)));
}
__device__ __forceinline__ void gemv_part(uint32_t wmbuf, int wp, int lane) {
    const uint32_t wa = wmbuf + wp * 512 + (8 * (lane >> 4) + (lane & 7)) * 32 + ((lane >> 3) & 1) * 16;
    float d[4] = {};
#pragma unroll
    for (int i = 0; i < 4; i++) {
        uint32_t A[4];
        const float2 v = lds2f(wmbuf + 28672 + (wp + 8 * i) * 32 + (lane & 3) * 8);
        ldsm4t(wa + (i < 3 || wp < 4 ? i : 0) * 4096, A);
        mma16816(d, A[0], A[1], A[2], A[3], __float_as_uint(v.x), __float_as_uint(v.y));
    }
    if ((lane & 3) == 0) {
        sts1(wmbuf + 29696 + (wp * 16 + (lane >> 2)) * 4, __float_as_uint(d[0]));
        sts1(wmbuf + 29696 + (wp * 16 + 8 + (lane >> 2)) * 4, __float_as_uint(d[2]));
    }
}
__device__ __forceinline__ uint32_t mod_word(float v, int col, uint32_t target) {
    v = bf_round(v);
    if ((col >= DM && col < 2 * DM) || (col >= 4 * DM && col < 5 * DM)) v += 1.f;
    return (pack2(v, 0.f) << 16) | (target & 0xFFFFu);
}
__device__ __forceinline__ const uint4* mod_src(int i, int r, int j, bool p2) {
    i = min(i, p2 ? 251 : 223);
    return (const uint4*)g_mod + (r & 7) * (6 * DM / 4) + (i < 224 ? (p2 ? 336 : 0) + i : (i < 238 ? 14 * j + i : 14 * j + i + 322));
}
__device__ __forceinline__ void mod_store(uint32_t sb, uint4 v, const uint4* src, int i) {
    const uint32_t tag = lds1(sb + M_EPOCH) + 1;
    while (__any_sync(~0u, (((v.x ^ tag) | (v.y ^ tag) | (v.z ^ tag) | (v.w ^ tag)) & 0xFFFFu) != 0u)) v = ld_relaxed4(src);
    if (i < 224) {
        const int isc = i >= 112, c4 = i - 112 * isc;
        const uint32_t a = sb + M_ST + (c4 >> 2) * 64 + (c4 & 1) * 32 + (c4 & 2) * 4 + (isc ? 0 : 4);
        sts1(a, __byte_perm(v.x, v.y, 0x7632));
        sts1(a + 16, __byte_perm(v.z, v.w, 0x7632));
    } else if (i < 252) {
        sts4(sb + M_G + (i - 224) * 16, make_uint4(v.x & 0xFFFF0000u, v.y & 0xFFFF0000u, v.z & 0xFFFF0000u, v.w & 0xFFFF0000u));
    }
}
__device__ __forceinline__ int pass_f(int fs, int ps) { return 224 * fs + ((fs & 1) ? (ps == 0 ? 96 : ps == 1 ? 32 : 0) : (ps == 0 ? 0 : ps == 1 ? 128 : 192)); }
__device__ __forceinline__ constexpr uint32_t slot_off(int l) { return l * 16384 + (l >= 10 ? 8192 : 0); }
constexpr uint64_t RING_ORDER = 0x6543C92B81A70ull;
constexpr uint32_t Y_XCH = 49152;
__device__ __forceinline__ constexpr int g1_slot(int s) { return s % 7; }
__device__ __noinline__ void x1_fix(const uint32_t* g, uint32_t sa, int s) {
#pragma unroll 1
    for (int k = 4 * s; k < 4 * s + 4;) {
        const uint4 v = ld_relaxed4((const uint4*)(g + k * 256));
        sts4(sa + k * 1024, v);
        k += 2 * __all_sync(~0u, min(min(v.x, v.y), min(v.z, v.w)) != 0u);
    }
    __syncwarp();
}
struct LnRow { uint32_t nm, hi, lo; };
__device__ __forceinline__ LnRow ln_coeffs(float mean, float msq) {
    const float var = bf_round(fmaxf(msq - mean * mean, 0.f));
    float sd;
    asm("sqrt.approx.f32 %0, %1;" : "=f"(sd) : "f"(bf_round(var + 1e-5f)));
    const float inv = rcp(bf_round(sd)), hi = bf_round(inv);
    LnRow c;
    c.nm = pack2(-bf_round(mean) * hi, -bf_round(mean) * hi);
    c.hi = pack2(hi, hi);
    c.lo = pack2(inv - hi, inv - hi);
    return c;
}
__device__ __forceinline__ uint32_t ln_norm(uint32_t x, const LnRow& c) {
    return hfma2(x, c.hi, c.nm);
}
__device__ __forceinline__ uint32_t ln_mod(uint32_t y, uint32_t sc, uint32_t sh) {
    return hfma2(y, sc, sh);
}

#define LOADW bulk_e(dst, g_wd + (size_t)((f >> 5) * 4 + nq) * 1792, 7168, bar);
template <int sec> __device__ __forceinline__ void ring_loader(const Params& p, uint32_t sb_, int r_, int j_, int lane) {
    const uint32_t sb = opaque(sb_);
    const int r = opaque(r_), j = opaque(j_), nq = j >> 1, fs = 4 * (j & 1) + nq;
    const int fa = pass_f(fs, 0), fb = pass_f(fs, 1), fc = pass_f(fs, 2);
    const uint32_t* h2src = (const uint32_t*)__shfl_sync(~0u, (unsigned long long)(p.actb + (size_t)r * RB_WORDS + RB_H2), 0);
    const CUtensorMap* gmap = (const CUtensorMap*)__shfl_sync(~0u, (unsigned long long)(&p.ga + sec), 0);
#define BAR(i) (sb + M_BAR + 8 * (i))
#define kh (j & 1)
            int sl = 0;
#pragma unroll 1
            for (int s = 0; s < 21; s++) {
                if (s == 7) { wait_flags(g_flag + (8 * r + j) * 192 + 96 + lane, lds1(sb + M_EPOCH) + 1, 0xFFFFu); fence_async_global(); }
                if (s >= 1 && s < 6) mbar_wait(BAR(B_FULL + s - 1), 0);
                mbar_wait(BAR(B_EMPTY + sl), s >= 7 && s < 14);
                expect_e(BAR(B_FULL + sl), 8192);
                tma3_e(sb + slot_off(sl) + sec * 8192, gmap + (s < 14 ? 0 : 2), 0, s < 14 ? 32 * s : 64 * sl, (s < 14 ? fa : fb) >> 6, BAR(B_FULL + sl));
                sl = sl == 6 ? 0 : sl + 1;
            }
#pragma unroll 1
            for (int s = 0; s < 7; s++) {
                const uint32_t bar = BAR(B_FULL + s);
                uint32_t dst = sb + slot_off(s) + sec * 4096;
                mbar_wait(BAR(B_EMPTY + s), 1);
                expect_e(bar, s < 3 ? 8192 : s > 3 ? 7168 : sec ? 4096 : 4096 + 7168);
                if (s < 4) tma3_e(dst, gmap + 4, 0, 128 * s, fc >> 5, bar);
                if (s < 3) tma3_e(dst + 8192, gmap + 4, 0, 128 * s + 64, fc >> 5, bar);
                else if (s > 3 || !sec) {
                    const int f = s == 3 ? fc : (s < 6 ? fa + 64 * (s - 4) : fb) + 32 * sec;
                    dst = sb + slot_off(s) + (s == 3 || sec ? 8192 : 0);
                    LOADW
                }
            }
            if (!sec) PROFH(3);
            if (sec) asm volatile("prefetch.tensormap [%0];" ::"l"(&p.om) : "memory");
            int e = 0;
#pragma unroll 1
            for (int grp = 0; grp < 9; grp++) {
                const int ps = grp >= 6 ? 2 : grp >= 3 ? 1 : 0;
                int sidx = grp - 3 * ps;
                if (sec && sidx == 0) { mbar_wait(BAR(B_HRDY + ps), 0); fence_async_global(); }
                sidx += sidx >= nq;
                int f = pass_f(4 * kh + sidx, ps);
#pragma unroll 1
                for (int k = 4 >> ps; k > 0; k--, e++, f += 32) {
                    sl = (RING_ORDER >> (4 * (e < 13 ? e : e - 13))) & 15;
                    const uint32_t dst = sb + slot_off(sl), bar = BAR(B_FULL + sl);
                    mbar_wait(BAR(B_EMPTY + sl), e >= 13);
                    if (e >= WIN) mbar_wait(BAR(B_FULL + ((RING_ORDER >> (4 * (e - WIN < 13 ? e - WIN : e - WIN - 13))) & 15)), e - WIN >= 13);
                    expect_e(bar, sec ? 8192 : 7168);
                    if (!sec) { LOADW }
                    else bulk_e(dst + 8192, h2src + f * 64, 8192, bar);
                }
            }
            if (!sec) PROFH(4);
}

#define PROF_PARAMS
#define PROF_ARGS
__device__ __noinline__ void helper_late(const Params& p, int r_, int j_, int warp_ PROF_PARAMS) {
    extern __shared__ __align__(1024) unsigned char smem[];
    const uint32_t sb = (uint32_t)__cvta_generic_to_shared(smem);
    const int r = opaque(r_), j = opaque(j_), warp = opaque(warp_), nq = j >> 1, b = 8 * r + j;
    uint32_t* const act = (uint32_t*)__shfl_sync(~0u, (unsigned long long)(p.actb + (size_t)r * RB_WORDS), 0);
    {
        const int lane = fresh_tid() & 31;
        const uint32_t target = lds1(sb + M_EPOCH) + 1;
        if (warp == 8) { expect_e(BAR(B_XCH), 7168); expect_e(BAR(B_XCH + 1), 7168); }
            if (warp == 9) {
#pragma unroll 1
                for (int kv = 0; kv < 2; kv++) {
                    mbar_wait(BAR(B_PUB + kv), 0);
                    wait_flags(g_flag + b * 192 + lane, target, (r >= 2 ? 6u : r == 1 ? 2u : 0u) << (8 * kv));
                    fence_async_global();
                    const uint32_t dst = sb + OFF_Y + (kv ? Y_VR : Y_K);
                    expect_e(BAR(B_KRFULL + kv), r >= 2 ? 28672 : r == 1 ? 14336 : 0);
                    if (r >= 2) bulk_e(dst, act - 2 * RB_WORDS + RB_KV + j * 7168 + kv * 3584, 14336, BAR(B_KRFULL + kv));
                    if (r >= 1) bulk_e(dst + 14336, act - RB_WORDS + RB_KV + j * 7168 + kv * 3584, 14336, BAR(B_KRFULL + kv));
                    if (kv == 0) { PROFH(8); }
                }
            } else if (warp == 8) {
                uint4 v[8];
                mbar_wait(BAR(B_WOFULL), 0);
#pragma unroll
                for (int k = 0; k < 8; k++) v[k] = ld_relaxed4(mod_src(lane + 32 * k, r, j, true));
#pragma unroll
                for (int k = 0; k < 8; k++) mod_store(sb, v[k], mod_src(lane + 32 * k, r, j, true), lane + 32 * k);
                warp_arrive(BAR(B_MOD1));
            } else if (warp == 11) {
                if (kh == 1 && r < 14) {
                    const uint32_t wmbuf = sb + OFF_X + HALF;
                    const int mcol = 2 * DM + 32 * (4 * r + nq);
                    mbar_wait(BAR(B_XFREE), 0);
                    tma3_e(wmbuf, &p.wm2, mcol, 0, 0, BAR(B_WMFULL));
                    tma3_e(wmbuf + 14336, &p.wm2, mcol, 224, 0, BAR(B_WMFULL));
#pragma unroll 1
                    for (int wd = lane; wd < 224; wd += 32) {
                        const uint32_t cb = __ldg((const uint32_t*)p.c + wd);
                        sts1(wmbuf + 28672 + (wd >> 3) * 32 + (wd & 3) * 8 + (wd & 4), pack2(silu_bf(cb & 0xFFFFu), silu_bf(cb >> 16)));
                    }
                    __syncwarp();
                    mbar_wait(BAR(B_WMFULL), 0);
                    const uint32_t wa = wmbuf + (8 * (lane >> 4) + (lane & 7)) * 64 + ((lane >> 3) & 1) * 16;
                    float d[2][4] = {};
#pragma unroll 4
                    for (int ks = 0; ks < 28; ks++) {
                        uint32_t A[8];
                        ldsm4t(wa + ks * 1024, A); ldsm4t(wa + ks * 1024 + 32, A + 4);
                        const float2 v = lds2f(wmbuf + 28672 + ks * 32 + (lane & 3) * 8);
                        mma16816(d[0], A[0], A[1], A[2], A[3], __float_as_uint(v.x), __float_as_uint(v.y));
                        mma16816(d[1], A[4], A[5], A[6], A[7], __float_as_uint(v.x), __float_as_uint(v.y));
                    }
                    const int q = lane & 3, col = mcol + 8 * q + (lane >> 2);
                    const uint32_t word = mod_word(q == 0 ? d[0][0] : q == 1 ? d[0][2] : q == 2 ? d[1][0] : d[1][2], col, target);
#pragma unroll
                    for (int i = 0; i < 8; i++) st_relaxed(g_mod + i * 6 * DM + col, word);
                }
                warp_arrive(BAR(B_WMFREE));
                mbar_wait(BAR(B_VRFULL), 0);
                l2_prefetch_e((const char*)p.wg + (size_t)b * 12544, 12544);
                l2_prefetch_e((const char*)p.wu + (size_t)b * 12544, 12544);
#pragma unroll 1
                for (int k = 0; k < (r < 12 ? 2 : 1); k++) {
                    const int u = 28 * kh + r + 16 * k;
                    expect_e(BAR(B_XFULL + k), 7168);
                    tma3_e(sb + OFF_Y + 102400, &p.dn, 0, 32 * u, 7 * j, BAR(B_XFULL + k));
                    tma3_e(sb + OFF_Y + 102400 + 3584, &p.dn, 0, 32 * u, 7 * (j ^ 1), BAR(B_XFULL + k));
                    mbar_wait(BAR(B_XFULL + k), 1);
                    asm volatile("{\n.reg .pred p;\nelect.sync _|p, 0xffffffff;\n@p cp.async.bulk.global.shared::cta.bulk_group [%0], [%1], 7168;\n"
                                 "cp.async.bulk.commit_group;\ncp.async.bulk.wait_group 0;\n}" ::"l"(g_wd + (size_t)(u * 4 + nq) * 1792), "r"(sb + OFF_Y + 102400) : "memory");
                    __syncwarp();
                }
                warp_arrive(BAR(B_FULLK));
                fence_gpu();
                if (lane < 16) st_relaxed(g_flag + (8 * lane + j) * 192 + 96 + r, target);
            }
        if (warp == 8 || warp == 11) {
            const int sec = warp == 11;
            if (sec) ring_loader<1>(p, sb, r, j, lane); else ring_loader<0>(p, sb, r, j, lane);
            mbar_wait(BAR(B_DONE), 0);
        } else if (warp == 9) {
#pragma unroll
            for (int ev = 0; ev < 4; ev++) { expect_e(BAR(B_GFULL + ev), ev < 2 ? HALF / 2 : 16384); expect_e(BAR(B_XFULL + 2 + ev), ev < 2 ? HALF / 2 : HALF - 16384); }
            mbar_wait(BAR(B_PUB + 2), 0);
            expect_e(BAR(B_FULLV), 4096); expect_e(BAR(B_FULLQ), 4096);
            const int par = (target - 1) & 1;
#pragma unroll 1
            for (int ev = 0; ev < 4; ev++) {
                if (ev == 1) { mbar_wait(BAR(B_FULLK), 1); mbar_wait(BAR(B_PUB + 3), 0); }
                const int tile = (ev & 1) + (ev >> 1) * par * 2;
                const uint32_t dst = sb + (ev == 0 ? OFF_X : OFF_Y + (ev & 1) * HALF), first = ev < 2 ? HALF / 2 : 16384;
                const char* src = (const char*)(act + RB_O + ((ev >> 1) * 2 + tile) * 14336);
                wait_flags(g_flag + b * 192 + (ev < 2 ? 32 : 64 + 32 * ev) + lane, target, ev < 2 ? 0xFFu << (8 * ev) : ~0u);
                fence_async_global();
                if (ev >= 2) bulk_e(sb + OFF_X + X_STAT + (ev & 1) * 49152, act + RB_ST + tile * 1024, 4096, BAR(B_FULLV + (ev & 1)));
                bulk_e(dst, src, first, BAR(B_GFULL + ev));
                bulk_e(dst + first, src + first, HALF - first, BAR(B_XFULL + 2 + ev));
                if (ev) PROFH(4 + ev);
            }
            mbar_wait(BAR(B_XFULL + 5), 1);
#pragma unroll 1
            for (int hf = 0; hf < 2; hf++) {
                const int tile = (par ^ 1) * 2 + hf;
                uint4* xz = (uint4*)(act + RB_X1 + tile * 14336 + j * 1792) + lane;
#pragma unroll
                for (int i = 0; i < 14; i++) xz[i * 32] = make_uint4(0, 0, 0, 0);
                ((uint4*)(act + RB_ST + (tile * 8 + j) * 128))[lane] = make_uint4(0, 0, 0, 0);
            }
#pragma unroll 1
            for (int ps = 0; ps < 3; ps++) {
                mbar_wait(BAR(B_PUB + 6 + ps), 0);
                if (ps == 1) {
                    fence_gpu();
                    if (lane < 8) st_relaxed(g_flag + (8 * r + lane) * 192 + 72 + j, target);
                }
                wait_flags(g_flag + b * 192 + 64 + lane, target, (0x55u << kh) << (8 * ps));
                warp_arrive(BAR(B_HRDY + ps));
                PROFH(9 + ps);
            }
        } else {
#pragma unroll 1
            for (int k = 0; k < 9; k++) {
                if (k == 4 || k == 5 || k == 7) continue;
                uint32_t* fp = k < 2 ? g_flag + (b + 8 * lane) * 192 + k * 8 + lane : g_flag + (8 * r + lane) * 192 + 16 + k * 8 + j;
                mbar_wait(BAR(B_PUB + k), 0);
                fence_gpu();
                if (k < 2 ? (lane == 1 || lane == 2) : lane < 8) st_relaxed(fp, target);
                if (k >= 3 && k <= 5) PROFH(k - 3);
            }
        }
    }
}

__global__ void __cluster_dims__(2, 1, 1) __launch_bounds__(384, 1) fused_block_kernel(const __grid_constant__ Params p) {
    extern __shared__ __align__(1024) unsigned char smem[];
    const uint32_t sb = (uint32_t)__cvta_generic_to_shared(smem);
    const int tid = threadIdx.x, lane = tid & 31, warp = __shfl_sync(~0u, tid >> 5, 0);
    const int m = blockIdx.x >> 1;
    int r, nq;
    if (m < 4) { r = 15; nq = m; }
    else if (m < 36) { r = (m - 4) & 7; nq = (m - 4) >> 3; }
    else { nq = (m - 36) / 7; r = m - 28 - 7 * nq; }
    const int j = opaque(2 * nq + (blockIdx.x & 1)), b = 8 * r + j, fs = 4 * kh + nq;
#define act (p.actb + (size_t)r * RB_WORDS)
    if (warp == 10 && blockIdx.x < 112) {
#pragma unroll
        for (int i = 0; i < 4; i++) l2_prefetch_e(p.wmod + (size_t)(4 * blockIdx.x + i) * (6 * DM), 4 * DM);
    }
    if (warp == 11) l2_prefetch_e((const char*)p.x + (size_t)blockIdx.x * 14336, 14336);
    if (lane == 0 && warp < 9 && warp != 6 && warp != 7) {
        const int i0 = warp == 8 ? 0 : 8 + 8 * warp, cnt = warp == 0 || warp == 8 ? 1 : warp < 3 ? 2 : 8;
#pragma unroll
        for (int k = 0; k < 8; k++) if (i0 + k != B_WMFULL) mbar_init(BAR(i0 + k), cnt);
        if (warp == 8) mbar_init(BAR(B_WMFULL), 1);
        asm volatile("fence.mbarrier_init.release.cluster;" ::: "memory");
        fence_async_smem();
    }

    if (warp >= 8) {
        const int lane = fresh_tid() & 31;
        const bool early = kh == 0, gemv = r < 14;
        const int mcol = early ? 16 * (4 * r + nq) : 2 * DM + 32 * (4 * r + nq);
        const uint32_t wmbuf = sb + OFF_Y + HALF;
        if (warp == 8) {
            __syncwarp();
            expect_e(BAR(B_WMFULL), gemv ? 28672 >> early : 0);
            if (early && gemv) { tma3_e(wmbuf, &p.wm, mcol, 0, 0, BAR(B_WMFULL)); tma3_e(wmbuf + 7168, &p.wm, mcol, 224, 0, BAR(B_WMFULL)); }
#pragma unroll
            for (int kb = 0; kb < 7; kb++) {
                expect_e(BAR(B_XFULL + kb), 16384);
                tma3_e(sb + OFF_X + kb * 16384, &p.xm, 64 * kb, 128 * r, 0, BAR(B_XFULL + kb));
            }
        }
        asm volatile("setmaxnreg.dec.sync.aligned.u32 56;");
        if (warp == 9) {
#pragma unroll
            for (int i = 56; i < 64; i++) init_e(BAR(i), 1);
            fence_async_smem();
        }
        bar_arrive(0, 384);
        asm volatile("barrier.cluster.arrive.relaxed.aligned;" ::: "memory");
        if (warp == 8) {
            mbar_wait(BAR(B_XFULL), 0);
            l2_prefetch_e((const char*)p.wqkv + (size_t)b * 9408, 9408);
#pragma unroll 1
            for (int mt = 0; mt < 4; mt++) {
                if (mt == 1) bar_sync(9, 384);
                if (mt == 3) mbar_wait(BAR(B_WMFREE), 0);
                if (mt == 1 && early) mbar_wait(BAR(B_WMFREE), 0);
                if (mt) mbar_wait(BAR(mt == 1 ? B_FULLK : mt == 2 ? B_MOD1 : B_VRFULL), 0);
                const uint32_t bar = BAR(mt == 3 ? B_WOFULL : B_FULLK + mt), dst = sb + (mt < 2 ? OFF_Y : OFF_X) + (mt & 1) * HALF;
                const int c0 = (mt < 2 ? DM + DM * mt : 0) + 56 * j - 8 * kh;
                expect_e(bar, HALF);
                tma3_e(dst, mt == 3 ? &p.wo : &p.qkv, c0, 0, 0, bar);
                tma3_e(dst + HALF / 2, mt == 3 ? &p.wo : &p.qkv, c0, 224, 0, bar);
            }
        } else {
            if (warp == 10 && lane < 13) asm volatile("prefetch.tensormap [%0];" ::"l"(&p.wm + lane) : "memory");
            bar_sync(9, 384);
            if (warp == 11 && early) {
                const uint32_t target = lds1(sb + M_EPOCH) + 1;
                mbar_wait(BAR(B_GEMV), 0);
                float sum = 0.f;
#pragma unroll
                for (int i = 0; i < 8; i++) sum += *(const float*)(smem + OFF_Y + HALF + 29696 + (i * 16 + (lane & 15)) * 4);
                uint32_t* mg = g_mod + mcol + (lane & 15) + (lane >> 4) * 4 * 6 * DM;
                const uint32_t word = mod_word(sum, mcol, target);
                if (gemv) { st_relaxed(mg, word); st_relaxed(mg + 6 * DM, word); st_relaxed(mg + 12 * DM, word); st_relaxed(mg + 18 * DM, word); }
            }
        }
    }
    if (warp < 8) {
        const int w = (warp >> 2) ^ 1, wi = warp & 3;
#define COORDS const int t = fresh_tid() & 127, lane = t & 31, q = lane & 3, lr = lane >> 2, ra = 64 * w + 16 * wi + lr; \
        const uint32_t lx = (lane >> 4) ^ (lane & 7), mrow = (64 * w + 16 * wi + ((lane >> 3) & 1) * 8 + (lane & 7)) * 128; \
        (void)q; (void)lr; (void)ra; (void)lx; (void)mrow;
#define WAIT(i, par) mbar_wait_c(BAR(i), par)
        constexpr uint64_t DB128 = dconst(4096, 1024, 1);
        {
            const int wd = fresh_tid();
            const uint32_t cb = wd < 224 ? __ldg((const uint32_t*)p.c + wd) : 0u;
            if (wd == 255) sts1(sb + M_EPOCH, atomicAdd(&g_ticket, 1u) / NCTA);
            sts1(sb + OFF_Y + HALF + 28672 + (wd >> 3) * 32 + (wd & 3) * 8 + (wd & 4), pack2(silu_bf(cb & 0xFFFFu), silu_bf(cb >> 16)));
        }
        bar_arrive(9, 384);
        bar_sync(0, 384);
        asm volatile("barrier.cluster.arrive.relaxed.aligned;" ::: "memory");
        asm volatile("setmaxnreg.inc.sync.aligned.u32 224;");
        PROFC(0);
        uint32_t xr[16];
        {
            COORDS
            uint32_t h[112];
            LnRow ca, cb;
            const int mi = min(128 * w + t, 223);
            const uint4* msrc = mod_src(mi, r, j, false);
            uint4 mv;
            {
                float ds[4] = {}, da[2][4] = {}, db[2][4] = {};
                const uint32_t ONE2 = 0x3F803F80u;
#pragma unroll
                for (int kb = 0; kb < 7; kb++) {
                    if (kb == 0 && kh == 0) { WAIT(B_WMFULL, 0); gemv_part(sb + OFF_Y + HALF, warp, lane); warp_arrive(BAR(B_GEMV)); }
                    WAIT(B_XFULL + kb, 0);
#pragma unroll
                    for (int k4 = 0; k4 < 4; k4++) ldsm4(sb + OFF_X + mrow + kb * 16384 + (((2 * k4) ^ lx) << 4), h + 16 * kb + 4 * k4);
#pragma unroll
                    for (int k4 = 0; k4 < 4; k4++) {
                        const uint32_t* f = h + 16 * kb + 4 * k4;
                        mma16816(ds, f[0], f[1], f[2], f[3], ONE2, ONE2);
                        mma1688(da[0], f[0], f[1], f[0]); mma1688(db[0], f[0], f[1], f[1]);
                        mma1688(da[1], f[2], f[3], f[2]); mma1688(db[1], f[2], f[3], f[3]);
                    }
                }
#pragma unroll
                for (int i = 0; i < 4; i++) {
                    const int ch = 7 * j + 2 * i + (lane >> 4);
                    ldsm4(sb + OFF_X + mrow + (ch >> 3) * 16384 + (((ch ^ lane) & 7) << 4), xr + 4 * i);
                }
                mv = ld_relaxed4(msrc);
                warp_arrive(BAR(B_XFREE));
                float qa = (lr & 1) ? da[0][1] + da[1][1] : da[0][0] + da[1][0];
                float qb = (lr & 1) ? db[0][3] + db[1][3] : db[0][2] + db[1][2];
                const int src = (lane & ~3) | (lr >> 1);
                qa = __shfl_sync(~0u, qa, src);
                qb = __shfl_sync(~0u, qb, src);
                ca = ln_coeffs(ds[0] * (1.f / DM), qa * (1.f / DM));
                cb = ln_coeffs(ds[2] * (1.f / DM), qb * (1.f / DM));
#pragma unroll
                for (int i = 0; i < 4 * NPRE; i += 2) { h[i] = ln_norm(h[i], ca); h[i + 1] = ln_norm(h[i + 1], cb); }
            }
            PROFC(1);
            {
                float ak[28], av[28], aq[28];
                uint32_t kp[14], vp[14];
                const uint64_t bq0 = (DB128 & ~0xFFFFFFFFull) | (mkdesc(sb + OFF_X, DB128) + kh), bk0 = bq0 + (OFF_Y >> 4), bv0 = bk0 + (HALF >> 4);
                uint32_t* kvg = act + RB_KV + j * 7168 + (8 * w + 2 * wi) * 224 + lane;
                mod_store(sb, mv, msrc, mi);
                bar_sync(3, 256);
                if (warp == 0) warp_arrive(BAR(B_MOD1));
                WAIT(B_FULLK, 0);
                PROFC(2);
                reg_def<28>(ak);
#pragma unroll
                for (int g4 = 0; g4 < 4; g4++) {
#pragma unroll
                    for (int ks = 7 * g4; ks < 7 * g4 + 7; ks++) {
                        const uint4 st = *(const uint4*)(smem + M_ST + ks * 64 + q * 16);
                        if (ks >= NPRE) {
                            h[4 * ks] = ln_norm(h[4 * ks], ca); h[4 * ks + 1] = ln_norm(h[4 * ks + 1], cb);
                            h[4 * ks + 2] = ln_norm(h[4 * ks + 2], ca); h[4 * ks + 3] = ln_norm(h[4 * ks + 3], cb);
                        }
                        h[4 * ks] = ln_mod(h[4 * ks], st.x, st.y); h[4 * ks + 1] = ln_mod(h[4 * ks + 1], st.x, st.y);
                        h[4 * ks + 2] = ln_mod(h[4 * ks + 2], st.z, st.w); h[4 * ks + 3] = ln_mod(h[4 * ks + 3], st.z, st.w);
                    }
                    WG_FENCE();
#pragma unroll
                    for (int ks = 7 * g4; ks < 7 * g4 + 7; ks++) wgmma_rl_56(ak, h[4 * ks], h[4 * ks + 1], h[4 * ks + 2], h[4 * ks + 3], bk0 + ks * 128, ks != 0);
                }
                WG_COMMIT();
                PROFC(3);
                reg_def<28>(av);
                WG_WAIT(0);
                reg_fence<28>(ak);
#pragma unroll
                for (int g = 0; g < 7; g++) {
                    kp[2 * g] = pack2(ak[4 * g], ak[4 * g + 1]); kp[2 * g + 1] = pack2(ak[4 * g + 2], ak[4 * g + 3]);
                    kvg[g * 32] = kp[2 * g]; kvg[224 + g * 32] = kp[2 * g + 1];
                }
                warp_arrive(BAR(B_PUB));
                PROFC(4);
                WAIT(B_FULLV, 0);
                WG_FENCE();
#pragma unroll
                for (int ks = 0; ks < 28; ks++) wgmma_rl_56(av, h[4 * ks], h[4 * ks + 1], h[4 * ks + 2], h[4 * ks + 3], bv0 + ks * 128, ks != 0);
                WG_COMMIT();
                reg_def<28>(aq);
                WAIT(B_FULLQ, 0);
                WG_FENCE();
#pragma unroll
                for (int ks = 0; ks < VPRE; ks++) wgmma_rl_56(aq, h[4 * ks], h[4 * ks + 1], h[4 * ks + 2], h[4 * ks + 3], bq0 + ks * 128, ks != 0);
                WG_COMMIT();
                WG_WAIT(1);
                reg_fence<28>(av);
#pragma unroll
                for (int g = 0; g < 7; g++) {
                    vp[2 * g] = pack2(av[4 * g], av[4 * g + 1]); vp[2 * g + 1] = pack2(av[4 * g + 2], av[4 * g + 3]);
                    kvg[3584 + g * 32] = vp[2 * g]; kvg[3584 + 224 + g * 32] = vp[2 * g + 1];
                }
                warp_arrive(BAR(B_PUB + 1));
                PROFC(5);
                WG_FENCE();
#pragma unroll
                for (int ks = VPRE; ks < 28; ks++) wgmma_rl_56(aq, h[4 * ks], h[4 * ks + 1], h[4 * ks + 2], h[4 * ks + 3], bq0 + ks * 128, ks != 0);
                WG_COMMIT();
                WAIT(B_PUB + 1, 0);
                const uint32_t rg = 8 * w + 2 * wi + ((lane >> 3) & 1);
                const uint32_t ko = sb + OFF_Y + Y_KOWN + rg * 896 + (lane & 7) * 16, qo = sb + OFF_Y + Y_Q + rg * 1024 + (lane >> 4) * 128 + (lane & 7) * 16;
#pragma unroll
                for (int g = 0; g < 6; g += 2) {
                    stsm4(ko + (g + (lane >> 4)) * 128, kp[2 * g], kp[2 * g + 1], kp[2 * g + 2], kp[2 * g + 3]);
                    stsm4(ko + (Y_VOWN - Y_KOWN) + (g + (lane >> 4)) * 128, vp[2 * g], vp[2 * g + 1], vp[2 * g + 2], vp[2 * g + 3]);
                }
                stsm4(ko + (lane >> 4) * (Y_VOWN - Y_KOWN) + 6 * 128, kp[12], kp[13], vp[12], vp[13]);
                WG_WAIT(0);
                reg_fence<28>(aq);
                __syncwarp();
                if (lane < 3 && w == 1) mbar_arrive(BAR(B_EMPTY + lane));
                uint32_t qp[14];
#pragma unroll
                for (int i = 0; i < 14; i++) qp[i] = pack2(aq[2 * i], aq[2 * i + 1]);
                stsm4(qo, qp[0], qp[1], qp[2], qp[3]);
                stsm4(qo + 256, qp[4], qp[5], q < 2 ? qp[6] : 0u, q < 2 ? qp[7] : 0u);
                stsm4(qo + 512, q < 2 ? 0u : qp[6], q < 2 ? 0u : qp[7], qp[8], qp[9]);
                stsm4(qo + 768, qp[10], qp[11], qp[12], qp[13]);
                fence_async_smem();
                if (w == 0) { bar_arrive(4, 256); bar_sync(1, 128); } else { bar_arrive(5, 256); bar_sync(4, 256); }
            }
        }
        PROFC(6);
        WAIT(B_KRFULL, 0);
        PROFC(7);
        {
#pragma unroll 1
            for (int hf = 0; hf < 2; hf++) {
                COORDS
                if (hf > w) bar_sync(5, 256);
                float s[160];
                const float CS = 0.18898223650461361f * 1.4426950408889634f;
                const float NEG = __int_as_float(0xFF800000);
                constexpr uint64_t DQ = dconst(128, 1024, 0), DK = dconst(128, 896, 0);
                {
                    const uint32_t qd = mkdesc(sb + OFF_Y + Y_Q + hf * 8192 + w * 512, DQ), kd = mkdesc(sb + OFF_Y + Y_K + hf * 8 * 896 + w * 384, DK);
                    reg_def<160>(s);
                    WG_FENCE();
                    wgmma_sk_160<DQ, DK>(s, qd, kd, 0);
                    wgmma_sk_160<DQ, DK>(s, qd + 16, kd + 16, 1);
                    wgmma_sk_160<DQ, DK>(s + 80, qd, kd + 20 * 56, 0);
                    wgmma_sk_160<DQ, DK>(s + 80, qd + 16, kd + 20 * 56 + 16, 1);
                    WG_COMMIT();
                    WG_WAIT(0);
                    reg_fence<160>(s);
                }
                if (r < 2) {
                    const int pmin = 4 - 2 * r - hf;
#pragma unroll
                    for (int p4 = 0; p4 < 4; p4++)
                        if (p4 < pmin) {
#pragma unroll
                            for (int i = 0; i < 32; i++) asm volatile("mov.b32 %0, 0xFF800000;" : "=f"(s[32 * p4 + i]));
                        }
                }
                const bool c0 = 2 * q > lr, c1 = 2 * q + 1 > lr;
#pragma unroll
                for (int pp = 0; pp < 4; pp++) {
                    const bool me = pp == wi;
                    float* e = s + 8 * pp;
                    if (me && !c0) { e[0] = NEG; e[6] = NEG; }
                    if (me && !c1) { e[1] = NEG; e[7] = NEG; }
                    if (me) { e[2] = NEG; e[3] = NEG; }
                    e = s + 8 * (pp + 16);
                    if (me && c0) { e[0] = NEG; e[6] = NEG; }
                    if (me && c1) { e[1] = NEG; e[7] = NEG; }
                    if (me) { e[4] = NEG; e[5] = NEG; }
                }
#pragma unroll
                for (int i = 0; i < 24; i++) s[i] = (i >> 3) < wi ? s[136 + i] : s[i];
                int i0 = 0x80000000, i1 = 0x80000000, i2 = 0x80000000, i3 = 0x80000000;
#pragma unroll
                for (int pp = 0; pp < 17; pp++) {
                    const float* e = s + 8 * pp;
                    i0 = __vimax3_s32(i0, __float_as_int(e[0]), __float_as_int(e[1])); i1 = __vimax3_s32(i1, __float_as_int(e[2]), __float_as_int(e[3]));
                    i2 = __vimax3_s32(i2, __float_as_int(e[4]), __float_as_int(e[5])); i3 = __vimax3_s32(i3, __float_as_int(e[6]), __float_as_int(e[7]));
                }
                i0 = max(i0, i2); i1 = max(i1, i3);
                i0 = max(i0, __shfl_xor_sync(~0u, i0, 1)); i1 = max(i1, __shfl_xor_sync(~0u, i1, 1));
                i0 = max(i0, __shfl_xor_sync(~0u, i0, 2)); i1 = max(i1, __shfl_xor_sync(~0u, i1, 2));
                if (__any_sync(~0u, (i0 | i1) < 0)) {
                    uint32_t u0 = ~0u, u1 = ~0u, u2 = ~0u, u3 = ~0u;
#pragma unroll
                    for (int pp = 0; pp < 17; pp++) {
                        const float* e = s + 8 * pp;
                        u0 = __vimin3_u32(u0, __float_as_uint(e[0]), __float_as_uint(e[1])); u1 = __vimin3_u32(u1, __float_as_uint(e[2]), __float_as_uint(e[3]));
                        u2 = __vimin3_u32(u2, __float_as_uint(e[4]), __float_as_uint(e[5])); u3 = __vimin3_u32(u3, __float_as_uint(e[6]), __float_as_uint(e[7]));
                    }
                    u0 = min(u0, u2); u1 = min(u1, u3);
                    u0 = min(u0, __shfl_xor_sync(~0u, u0, 1)); u1 = min(u1, __shfl_xor_sync(~0u, u1, 1));
                    u0 = min(u0, __shfl_xor_sync(~0u, u0, 2)); u1 = min(u1, __shfl_xor_sync(~0u, u1, 2));
                    if (i0 < 0) i0 = u0;
                    if (i1 < 0) i1 = u1;
                }
                const float ma = __int_as_float(i0), mb = __int_as_float(i1);
                const float na = -ma * CS, nb = -mb * CS;
                PROFC(8 + 3 * hf);
                {
                    WAIT(B_VRFULL, 0);
                    float o[16] = {}, rs[4] = {};
                    const uint32_t va = sb + OFF_Y + Y_VR + (8 * hf + ((lane >> 3) & 1)) * 896 + (3 * w + (lane >> 4)) * 128 + (lane & 7) * 16;
                    constexpr uint32_t OWN = Y_VOWN - 32 * 896;
#pragma unroll
                    for (int pp = 0; pp < 17; pp++) {
                        uint32_t B[8];
                        const uint32_t v = va + pp * 1792 + (pp < 3 ? (pp < wi ? 17 * 1792 + OWN : 0) : pp == 16 ? OWN : pp >= 12 ? hf * OWN : 0);
                        ldsm4t(v, B); ldsm4t(v + 256, B + 4);
                        float e[8];
#pragma unroll
                        for (int i = 0; i < 8; i++) e[i] = ex2(fmaf(s[8 * pp + i], CS, (i & 2) ? nb : na));
                        const uint32_t p0 = pack2(e[0], e[1]), p1 = pack2(e[2], e[3]), p2 = pack2(e[4], e[5]), p3 = pack2(e[6], e[7]);
                        mma16816(rs, p0, p1, p2, p3, 0x3F803F80u, 0x3F803F80u);
#pragma unroll
                        for (int g = 0; g < 4; g++) mma16816(o + 4 * g, p0, p1, p2, p3, B[2 * g], B[2 * g + 1]);
                    }
                    PROFC(9 + 3 * hf);
                    const float ia = rcp(rs[0]), ib = rcp(rs[2]);
                    uint32_t* og = act + RB_O + hf * 14336 + (7 * j + 3 * w) * 256 + wi * 64 + lane;
#pragma unroll
                    for (int g = 0; g < 4; g++) {
                        if ((g == 3 - 3 * w) ? ((q >> 1) == w) : true) {
                            og[g * 256] = pack2(o[4 * g] * ia, o[4 * g + 1] * ia);
                            og[g * 256 + 32] = pack2(o[4 * g + 2] * ib, o[4 * g + 3] * ib);
                        }
                    }
                    warp_arrive(BAR(B_PUB + 2 + hf));
                    PROFC(10 + 3 * hf);
                }
            }
        }
        uint32_t x1p[14];
        COORDS
        constexpr uint64_t DT = dconst(1024, 128, 0);
        const uint32_t epoch = lds1(sb + M_EPOCH);
        const int tile = opaque((epoch & 1) * 2 + w);
        {
            float ac[28];
            const uint32_t ad = mkdesc(sb + (w ? OFF_Y + HALF : OFF_X), DT), bd = mkdesc(sb + OFF_X + HALF, DB128) + kh;
            WAIT(B_WOFULL, 0);
            WAIT(B_MOD1, 1);
            WAIT(B_GFULL + w, 0);
            PROFC(28);
            reg_def<28>(ac);
#pragma unroll 1
            for (int u = 0; u < 4; u++) {
                if (u == 2) WAIT(B_XFULL + 2 + w, 1);
                WG_FENCE();
#pragma unroll
                for (int i = 0; i < 7; i++) wgmma_ss_56<DT, DB128>(ac, ad + (7 * u + i) * 128, bd + (7 * u + i) * 128, (u | i) != 0);
            }
            WG_COMMIT();
            WG_WAIT(0);
            reg_fence<28>(ac);
            PROFC(14);
            __syncwarp();
            if (lane < 3) mbar_arrive(BAR(B_EMPTY + 4 - w + lane));
            if (lane < 3 && w == 0) mbar_arrive(BAR(B_EMPTY + lane));
            float ds[4] = {}, da[4] = {}, db[4] = {};
            uint32_t* xo = act + RB_X1 + tile * 14336 + 7 * j * 256 + wi * 64 + lane;
#pragma unroll
            for (int g = 0; g < 7; g++) {
                const float2 ga = *(const float2*)(smem + M_G + (8 * g + 2 * q) * 4);
                x1p[2 * g] = pack2(fmaf(ga.x, ac[4 * g], bf_lo(xr[2 * g])), fmaf(ga.y, ac[4 * g + 1], bf_hi(xr[2 * g])));
                x1p[2 * g + 1] = pack2(fmaf(ga.x, ac[4 * g + 2], bf_lo(xr[2 * g + 1])), fmaf(ga.y, ac[4 * g + 3], bf_hi(xr[2 * g + 1])));
                st_relaxed(xo + g * 256, nz(x1p[2 * g])); st_relaxed(xo + g * 256 + 32, nz(x1p[2 * g + 1]));
                mma1688(ds, x1p[2 * g], x1p[2 * g + 1], 0x3F803F80u);
                mma1688(da, x1p[2 * g], x1p[2 * g + 1], x1p[2 * g]);
                mma1688(db, x1p[2 * g], x1p[2 * g + 1], x1p[2 * g + 1]);
            }
            const int src = (lane & ~3) | (lr >> 1);
            const float qa = __shfl_sync(~0u, (lr & 1) ? da[1] : da[0], src), qb = __shfl_sync(~0u, (lr & 1) ? db[3] : db[2], src);
            const float kk = (q & 1) ? ((q & 2) ? qb : qa) : ((q & 2) ? ds[2] : ds[0]);
            st_relaxed(act + RB_ST + ((tile * 8 + j) * 64 + 16 * wi + lr + 4 * (q & 2)) * 2 + (q & 1), nz(__float_as_uint(kk)));
            if (lane < 8) st_relaxed(g_flag + (8 * r + lane) * 192 + 128 + 32 * w + 4 * j + wi, epoch + 1);
        }
        PROFC(15);
        uint32_t h2a[32], h2b[24];
        {
            const int fa = pass_f(fs, 0), fb = pass_f(fs, 1), fc = pass_f(fs, 2);
            uint32_t* h2g = act + RB_H2 + (8 * w + 2 * wi) * 32 + lane;
            const uint32_t a0 = mkdesc(sb + OFF_Y + w * HALF, DT);
            {
                LnRow ca, cb;
                {
                    const uint32_t* sg = act + RB_ST + ((tile * 8 + 2 * q) * 64 + 16 * wi + lr) * 2;
                    uint2 u[4];
                    WAIT(B_FULLV + w, 1);
                    PROFC(16);
#pragma unroll
                    for (int i = 0; i < 4; i++) { const float2 v = lds2f(sb + OFF_X + X_STAT + w * 49152 + ((2 * q + (i >> 1)) * 64 + 16 * wi + lr + 8 * (i & 1)) * 8); u[i] = make_uint2(__float_as_uint(v.x), __float_as_uint(v.y)); }
                    while (__any_sync(~0u, min(min(min(u[0].x, u[0].y), min(u[1].x, u[1].y)), min(min(u[2].x, u[2].y), min(u[3].x, u[3].y))) == 0u)) {
#pragma unroll
                        for (int i = 0; i < 4; i++) u[i] = ld_relaxed2(sg + (i >> 1) * 128 + (i & 1) * 16);
                    }
                    warp_arrive(BAR(B_EMPTY + 3 + 3 * w));
                    float v[4] = {__uint_as_float(u[0].x) + __uint_as_float(u[2].x), __uint_as_float(u[0].y) + __uint_as_float(u[2].y),
                                  __uint_as_float(u[1].x) + __uint_as_float(u[3].x), __uint_as_float(u[1].y) + __uint_as_float(u[3].y)};
#pragma unroll
                    for (int i = 0; i < 4; i++) { v[i] += __shfl_xor_sync(~0u, v[i], 1); v[i] += __shfl_xor_sync(~0u, v[i], 2); }
                    ca = ln_coeffs(v[0] * (1.f / DM), v[1] * (1.f / DM));
                    cb = ln_coeffs(v[2] * (1.f / DM), v[3] * (1.f / DM));
                }
                const uint32_t ha = sb + OFF_Y + w * HALF + (lane >> 4) * 1024 + (2 * wi + ((lane >> 3) & 1)) * 128 + (lane & 7) * 16;
                const uint32_t sta = sb + M_ST + q * 16;
                const uint32_t* xg = act + RB_X1 + tile * 14336 + (lane >> 4) * 256 + wi * 64 + (lane & 15) * 4;
                uint32_t x[8];
                const uint32_t xs = sb + OFF_Y + w * HALF + (lane >> 4) * 1024 + wi * 256 + (lane & 15) * 16;
                uint4 st[2];
                auto load = [&](int s) {
                    if (s == 4) mbar_wait_c(BAR(B_XFULL + 4 + w), 1);
                    ldsm4(ha + s * 4096, x); ldsm4(ha + s * 4096 + 2048, x + 4);
                    st[0] = lds4(sta + s * 128); st[1] = lds4(sta + s * 128 + 64);
                };
                auto prep = [&](int s, uint32_t* f) {
                    if (__any_sync(~0u, min(min(min(x[0], x[1]), min(x[2], x[3])), min(min(x[4], x[5]), min(x[6], x[7]))) == 0u)) {
                        WG_WAIT(0);
                        x1_fix(xg, xs, s);
                        ldsm4(ha + s * 4096, x); ldsm4(ha + s * 4096 + 2048, x + 4);
                    }
#pragma unroll
                    for (int i = 0; i < 2; i++) {
                        f[4 * i] = ln_mod(ln_norm(x[4 * i], ca), st[i].x, st[i].y); f[4 * i + 1] = ln_mod(ln_norm(x[4 * i + 1], cb), st[i].x, st[i].y);
                        f[4 * i + 2] = ln_mod(ln_norm(x[4 * i + 2], ca), st[i].z, st[i].w); f[4 * i + 3] = ln_mod(ln_norm(x[4 * i + 3], cb), st[i].z, st[i].w);
                    }
                    if (s < 13) load(s + 1);
                    stsm4(ha + s * 4096, f[0], f[1], f[2], f[3]); stsm4(ha + s * 4096 + 2048, f[4], f[5], f[6], f[7]);
                };
                float ac[128];
                uint32_t fr[3][8];
                uint64_t bd = (DB128 & ~0xFFFFFFFFull) | mkdesc(sb, DB128);
                reg_def<128>(ac);
                WAIT(B_GFULL + 2 + w, 0);
                load(0);
                prep(0, fr[0]);
                PROFC(17);
#pragma unroll
                for (int s = 0; s < 14; s++) {
                    const uint32_t* f = fr[s % 3];
                    WAIT(B_FULL + g1_slot(s), s >= 7);
                    WG_FENCE();
                    wgmma_rl_256(ac, f[0], f[1], f[2], f[3], bd, s != 0);
                    wgmma_rl_256(ac, f[4], f[5], f[6], f[7], bd + 128, 1);
                    bd += s == 6 ? p.zero - 6 * 1024ull : 1024;
                    WG_COMMIT();
                    if (s < 13) prep(s + 1, fr[(s + 1) % 3]);
                    if (s > 0) { WG_WAIT(1); warp_arrive(BAR(B_EMPTY + g1_slot(s - 1))); }
                }
                fence_async_smem();
                PROFC(18);
                WG_WAIT(0);
                reg_fence<128>(ac);
                warp_arrive(BAR(B_EMPTY + 6));
#pragma unroll
                for (int g = 0; g < 16; g++) {
                    h2a[2 * g] = hmul2(pack2_relu(ac[4 * g], ac[4 * g + 1]), pack2(ac[64 + 4 * g], ac[64 + 4 * g + 1]));
                    h2a[2 * g + 1] = hmul2(pack2_relu(ac[4 * g + 2], ac[4 * g + 3]), pack2(ac[64 + 4 * g + 2], ac[64 + 4 * g + 3]));
                }
                bar_sync(1 + w, 128);
            }
            PROFC(19);
            {
                float ac[64];
                reg_def<64>(ac);
                const uint32_t bx = mkdesc(sb, dconst(8192, 1024, 1));
#pragma unroll 1
                for (int s = 0; s < 7; s++) {
                    WAIT(B_FULL + s, 0);
                    const uint32_t ad = a0 + s * 512, bd = bx + (slot_off(s) >> 4);
                    WG_FENCE();
#pragma unroll
                    for (int k = 0; k < 4; k++) wgmma_ss_128<DT, DB128>(ac, ad + k * 128, bd + k * 128, (s | k) != 0);
                    WG_COMMIT();
                    if (s == 1) {
#pragma unroll
                        for (int g = 0; g < 16; g++) { h2g[(fa / 8 + g) * 512] = h2a[2 * g]; h2g[(fa / 8 + g) * 512 + 32] = h2a[2 * g + 1]; }
                        warp_arrive(BAR(B_PUB + 6));
                    }
                    if (s > 0) { WG_WAIT(1); warp_arrive(BAR(B_EMPTY + s - 1)); }
                }
                WG_WAIT(0);
                reg_fence<64>(ac);
                warp_arrive(BAR(B_EMPTY + 6));
#pragma unroll
                for (int g = 0; g < 8; g++) {
                    h2b[2 * g] = hmul2(pack2_relu(ac[4 * g], ac[4 * g + 1]), pack2(ac[32 + 4 * g], ac[32 + 4 * g + 1]));
                    h2b[2 * g + 1] = hmul2(pack2_relu(ac[4 * g + 2], ac[4 * g + 3]), pack2(ac[32 + 4 * g + 2], ac[32 + 4 * g + 3]));
                }
            }
            PROFC(27);
            {
                float ac[32];
                reg_def<32>(ac);
                const uint32_t bx = mkdesc(sb, dconst(4096, 512, 2));
#pragma unroll 1
                for (int s = 0; s < 7; s++) {
                    WAIT(B_FULL + (s >> 1), 1);
                    const uint32_t ad = a0 + s * 512, bd = bx + s * 512;
                    WG_FENCE();
#pragma unroll
                    for (int k = 0; k < 4; k++) wgmma_ss_64<DT, dconst(4096, 512, 2)>(ac, ad + k * 128, bd + k * 64, (s | k) != 0);
                    WG_COMMIT();
                    if (s == 1) {
#pragma unroll
                        for (int g = 0; g < 8; g++) { h2g[(fb / 8 + g) * 512] = h2b[2 * g]; h2g[(fb / 8 + g) * 512 + 32] = h2b[2 * g + 1]; }
                        warp_arrive(BAR(B_PUB + 7));
                    }
                    if (s > 0 && !(s & 1)) {
                        WG_WAIT(1);
                        __syncwarp();
                        if (lane < 3) mbar_arrive(BAR(B_EMPTY + (s >> 1) - 1 + (lane ? 4 + 3 * lane : 0)));
                    }
                }
                WG_WAIT(0);
                reg_fence<32>(ac);
                PROFC(20);
#pragma unroll
                for (int g = 0; g < 4; g++) {
                    h2b[16 + 2 * g] = hmul2(pack2_relu(ac[4 * g], ac[4 * g + 1]), pack2(ac[16 + 4 * g], ac[16 + 4 * g + 1]));
                    h2b[16 + 2 * g + 1] = hmul2(pack2_relu(ac[4 * g + 2], ac[4 * g + 3]), pack2(ac[16 + 4 * g + 2], ac[16 + 4 * g + 3]));
                    h2g[(fc / 8 + g) * 512] = h2b[16 + 2 * g]; h2g[(fc / 8 + g) * 512 + 32] = h2b[16 + 2 * g + 1];
                }
                warp_arrive(BAR(B_PUB + 8));
                asm volatile("barrier.cluster.wait.aligned;" ::: "memory");
                if (lane == 0) {
                    uint32_t rb;
                    asm volatile("mapa.shared::cluster.u32 %0, %1, %2;" : "=r"(rb) : "r"(BAR(B_PEER)), "r"(kh ^ 1));
                    asm volatile("mbarrier.arrive.relaxed.cluster.shared::cluster.b64 _, [%0];" ::"r"(rb) : "memory");
                }
            }
        }
        PROFC(21);
        {
            float ac[56];
            reg_def<56>(ac);
            constexpr uint64_t DAN = dconst(2048, 128, 0);
            constexpr uint64_t DW = dconst(128, 512, 0);
            const uint32_t bx = mkdesc(sb, DW);
#pragma unroll
            for (int e = 3; e < 7; e++) {
                if (e > 3) WAIT(B_FULL + e, 1);
                const uint64_t bd = ((DW & ~0xFFFFFFFFull) | bx) + (slot_off(e) >> 4);
                const uint32_t* hh = e == 3 ? h2b + 8 : e < 6 ? h2a + 16 * (e - 4) : h2b;
                WG_FENCE();
#pragma unroll
                for (int k = e == 3 ? 2 : 0; k < 4; k++) wgmma_rl_112(ac, hh[4 * k], hh[4 * k + 1], hh[4 * k + 2], hh[4 * k + 3], bd + (k >> 1) * 512 + (k & 1) * 16, e > 3 || k > 2);
                WG_COMMIT();
                if (e > 3) { WG_WAIT(1); warp_arrive(BAR(B_EMPTY + e - 1)); }
            }
            PROFC(22);
            const uint32_t ax = mkdesc(sb + 8192 + w * 1024, DAN);
            uint32_t eb_ = BAR(B_EMPTY + 6);
            uint64_t ord = RING_ORDER;
#pragma unroll 1
            for (int e = 0; e < 21; e++) {
                const uint32_t sl = ord & 15, so = slot_off(sl) >> 4;
                ord = e == 12 ? RING_ORDER : ord >> 4;
                mbar_wait_c(BAR(B_FULL + sl), e >= 13);
                WG_FENCE();
                wgmma_ss_112<DAN, DW>(ac, ax + so, bx + so, 1);
                wgmma_ss_112<DAN, DW>(ac, ax + so + 256, bx + so + 16, 1);
                WG_COMMIT();
                WG_WAIT(1);
                warp_arrive(eb_);
                eb_ = BAR(B_EMPTY + sl);
            }
            mbar_wait_cluster(BAR(B_PEER), 0);
            WG_WAIT(0);
            reg_fence<56>(ac);
            PROFC(24);
            uint32_t rdst, rbar;
            asm volatile("mapa.shared::cluster.u32 %0, %1, %2;" : "=r"(rdst) : "r"(sb + OFF_Y + Y_XCH + w * HALF + t * 16), "r"(kh ^ 1));
            asm volatile("mapa.shared::cluster.u32 %0, %1, %2;" : "=r"(rbar) : "r"(BAR(B_XCH + w)), "r"(kh ^ 1));
#pragma unroll
            for (int g = 0; g < 3; g++)
                asm volatile("st.async.shared::cluster.mbarrier::complete_tx::bytes.v4.b32 [%0], {%1,%2,%3,%4}, [%5];" ::"r"(rdst + g * 2048),
                             "r"(pack2(ac[28 + 8 * g], ac[29 + 8 * g])), "r"(pack2(ac[30 + 8 * g], ac[31 + 8 * g])), "r"(pack2(ac[32 + 8 * g], ac[33 + 8 * g])),
                             "r"(pack2(ac[34 + 8 * g], ac[35 + 8 * g])), "r"(rbar) : "memory");
            asm volatile("st.async.shared::cluster.mbarrier::complete_tx::bytes.v2.b32 [%0], {%1,%2}, [%3];" ::"r"(rdst + 6144 - t * 8),
                         "r"(pack2(ac[52], ac[53])), "r"(pack2(ac[54], ac[55])), "r"(rbar) : "memory");
            mbar_wait_cluster(BAR(B_XCH + w), 0);
            PROFC(25);
            uint32_t op[14], rv[14];
#pragma unroll
            for (int g = 0; g < 3; g++) *(uint4*)(rv + 4 * g) = *(const uint4*)(smem + OFF_Y + Y_XCH + w * HALF + t * 16 + g * 2048);
            *(uint2*)(rv + 12) = *(const uint2*)(smem + OFF_Y + Y_XCH + w * HALF + 6144 + t * 8);
#pragma unroll
            for (int i = 0; i < 14; i++) {
                const float2 gb = *(const float2*)(smem + M_G + 224 + (8 * (i >> 1) + 2 * q) * 4);
                op[i] = pack2(fmaf(gb.x, ac[2 * i] + bf_lo(rv[i]), bf_lo(x1p[i])), fmaf(gb.y, ac[2 * i + 1] + bf_hi(rv[i]), bf_hi(x1p[i])));
            }
            WAIT(B_EMPTY + 4, 1);
            const uint32_t oc = sb + OUT_STAGE + warp * 1792;
            const uint32_t oa = oc + (((lane >> 3) & 1) * 8 + (lane & 7)) * 112 + (lane >> 4) * 16;
            stsm4(oa, op[0], op[1], op[2], op[3]); stsm4(oa + 32, op[4], op[5], op[6], op[7]); stsm4(oa + 64, op[8], op[9], op[10], op[11]);
            asm volatile("stmatrix.sync.aligned.m8n8.x2.shared.b16 [%0], {%1,%2};" ::"r"(oa + 96), "r"(op[12]), "r"(op[13]));
            fence_async_smem();
            __syncwarp();
            asm volatile("{\n.reg .pred p;\nelect.sync _|p, 0xffffffff;\n@p cp.async.bulk.tensor.3d.global.shared::cta.bulk_group [%0, {%2, %3, %4}], [%1];\n"
                         "cp.async.bulk.commit_group;\ncp.async.bulk.wait_group.read 0;\n}" ::"l"(&p.om), "r"(oc), "r"(56 * j), "r"(128 * r + 64 * w + 16 * wi), "r"(0) : "memory");
        }
        PROFC(26);
        bar_sync(1 + w, 128);
        if (wi == 0) warp_arrive(BAR(B_DONE));
        return;
    }
    helper_late(p, r, j, warp PROF_ARGS);
}

#undef act
typedef CUresult (*EncodeFn)(CUtensorMap*, CUtensorMapDataType, cuuint32_t, void*, const cuuint64_t*, const cuuint64_t*, const cuuint32_t*,
                             const cuuint32_t*, CUtensorMapInterleave, CUtensorMapSwizzle, CUtensorMapL2promotion, CUtensorMapFloatOOBfill);

static void make_map(EncodeFn fn, CUtensorMap* m, const void* ptr, uint64_t d0, uint64_t d1, uint64_t d2, uint64_t s1, uint64_t s2,
                     uint32_t b0, uint32_t b1, uint32_t b2, CUtensorMapSwizzle sw) {
    cuuint64_t dims[3] = {d0, d1, d2}, strides[2] = {s1, s2};
    cuuint32_t box[3] = {b0, b1, b2}, es[3] = {1, 1, 1};
    CUresult rc = fn(m, CU_TENSOR_MAP_DATA_TYPE_BFLOAT16, 3, (void*)ptr, dims, strides, box, es, CU_TENSOR_MAP_INTERLEAVE_NONE, sw,
                     CU_TENSOR_MAP_L2_PROMOTION_L2_128B, CU_TENSOR_MAP_FLOAT_OOB_FILL_NONE);
    (void)rc;
}

extern "C" void kernel_launch(void* const* d_in, const int* in_sizes, int n_in, void* d_out, int out_size) {
    (void)in_sizes; (void)n_in; (void)out_size;
    static EncodeFn fn = nullptr;
    static uint32_t* act_base = nullptr;
    if (!fn) {
        cudaDriverEntryPointQueryResult st;
        cudaGetDriverEntryPoint("cuTensorMapEncodeTiled", (void**)&fn, cudaEnableDefault, &st);
        void* a = nullptr;
        cudaGetSymbolAddress(&a, g_act);
        act_base = (uint32_t*)(((uintptr_t)a + 0xFFFFF) & ~(uintptr_t)0xFFFFF);
        cudaFuncSetAttribute(fused_block_kernel, cudaFuncAttributeMaxDynamicSharedMemorySize, SMEM_BYTES);
    }
    Params p;
    p.x = (const bf16*)d_in[0];
    const bf16* wqkv = (const bf16*)d_in[1];
    p.wqkv = wqkv;
    p.wop = (const bf16*)d_in[2];
    p.wg = (const bf16*)d_in[4];
    p.wu = (const bf16*)d_in[5];
    p.wd = (const bf16*)d_in[6];
    p.c = (const bf16*)d_in[7];
    p.wmod = (const bf16*)d_in[8];
    p.out = (bf16*)d_out;
    p.zero = 0;
    p.actb = act_base;
    make_map(fn, &p.wm, p.wmod, 2688, 448, 1, 5376, 5376 * 448, 16, 224, 1, CU_TENSOR_MAP_SWIZZLE_NONE);
    make_map(fn, &p.wm2, p.wmod, 2688, 448, 1, 5376, 5376 * 448, 32, 224, 1, CU_TENSOR_MAP_SWIZZLE_NONE);
    make_map(fn, &p.om, p.out, 448, 2048, 1, 896, 896 * 2048, 56, 16, 1, CU_TENSOR_MAP_SWIZZLE_NONE);
    make_map(fn, &p.xm, p.x, 448, 2048, 1, 896, 896 * 2048, 64, 128, 1, CU_TENSOR_MAP_SWIZZLE_128B);
    make_map(fn, &p.qkv, wqkv, 1344, 448, 1, 2688, 2688 * 448, 64, 224, 1, CU_TENSOR_MAP_SWIZZLE_128B);
    make_map(fn, &p.wo, p.wop, 448, 448, 1, 896, 896 * 448, 64, 224, 1, CU_TENSOR_MAP_SWIZZLE_128B);
    make_map(fn, &p.ga, p.wg, 64, 448, 28, 3584, 128, 64, 32, 2, CU_TENSOR_MAP_SWIZZLE_128B);
    make_map(fn, &p.ua, p.wu, 64, 448, 28, 3584, 128, 64, 32, 2, CU_TENSOR_MAP_SWIZZLE_128B);
    make_map(fn, &p.gb, p.wg, 64, 448, 28, 3584, 128, 64, 64, 1, CU_TENSOR_MAP_SWIZZLE_128B);
    make_map(fn, &p.ub, p.wu, 64, 448, 28, 3584, 128, 64, 64, 1, CU_TENSOR_MAP_SWIZZLE_128B);
    make_map(fn, &p.gc, p.wg, 32, 448, 56, 3584, 64, 32, 64, 1, CU_TENSOR_MAP_SWIZZLE_64B);
    make_map(fn, &p.uc, p.wu, 32, 448, 56, 3584, 64, 32, 64, 1, CU_TENSOR_MAP_SWIZZLE_64B);
    make_map(fn, &p.dn, p.wd, 8, 1792, 56, 896, 16, 8, 32, 7, CU_TENSOR_MAP_SWIZZLE_NONE);
    fused_block_kernel<<<NCTA, 384, SMEM_BYTES>>>(p);
}
```

```cpp
#include <cuda_runtime.h>
#include <cuda_bf16.h>
#include <cuda.h>
#include <stdint.h>

typedef __nv_bfloat16 bf16;

template<uint64_t CA, uint64_t CB> __device__ __forceinline__ void wgmma_sk_160(float* d, uint32_t da, uint32_t db, int sd) {
  asm volatile("{\n.reg .pred p;\n.reg .b64 a, b;\nsetp.ne.b32 p, %82, 0;\nmov.b64 a, {%80, %83};\nmov.b64 b, {%81, %84};\n"
    "wgmma.mma_async.sync.aligned.m64n160k16.f32.bf16.bf16 {%0,%1,%2,%3,%4,%5,%6,%7,%8,%9,%10,%11,%12,%13,%14,%15,%16,%17,%18,%19,%20,%21,%22,%23,%24,%25,%26,%27,%28,%29,%30,%31,%32,%33,%34,%35,%36,%37,%38,%39,%40,%41,%42,%43,%44,%45,%46,%47,%48,%49,%50,%51,%52,%53,%54,%55,%56,%57,%58,%59,%60,%61,%62,%63,%64,%65,%66,%67,%68,%69,%70,%71,%72,%73,%74,%75,%76,%77,%78,%79}, a, b, p, 1, 1, 0, 0;\n}\n"
    : "+f"(d[0]),"+f"(d[1]),"+f"(d[2]),"+f"(d[3]),"+f"(d[4]),"+f"(d[5]),"+f"(d[6]),"+f"(d[7]),"+f"(d[8]),"+f"(d[9]),"+f"(d[10]),"+f"(d[11]),"+f"(d[12]),"+f"(d[13]),"+f"(d[14]),"+f"(d[15]),"+f"(d[16]),"+f"(d[17]),"+f"(d[18]),"+f"(d[19]),"+f"(d[20]),"+f"(d[21]),"+f"(d[22]),"+f"(d[23]),"+f"(d[24]),"+f"(d[25]),"+f"(d[26]),"+f"(d[27]),"+f"(d[28]),"+f"(d[29]),"+f"(d[30]),"+f"(d[31]),"+f"(d[32]),"+f"(d[33]),"+f"(d[34]),"+f"(d[35]),"+f"(d[36]),"+f"(d[37]),"+f"(d[38]),"+f"(d[39]),"+f"(d[40]),"+f"(d[41]),"+f"(d[42]),"+f"(d[43]),"+f"(d[44]),"+f"(d[45]),"+f"(d[46]),"+f"(d[47]),"+f"(d[48]),"+f"(d[49]),"+f"(d[50]),"+f"(d[51]),"+f"(d[52]),"+f"(d[53]),"+f"(d[54]),"+f"(d[55]),"+f"(d[56]),"+f"(d[57]),"+f"(d[58]),"+f"(d[59]),"+f"(d[60]),"+f"(d[61]),"+f"(d[62]),"+f"(d[63]),"+f"(d[64]),"+f"(d[65]),"+f"(d[66]),"+f"(d[67]),"+f"(d[68]),"+f"(d[69]),"+f"(d[70]),"+f"(d[71]),"+f"(d[72]),"+f"(d[73]),"+f"(d[74]),"+f"(d[75]),"+f"(d[76]),"+f"(d[77]),"+f"(d[78]),"+f"(d[79])
    : "r"(da), "r"(db), "r"(sd), "n"((uint32_t)(CA >> 32)), "n"((uint32_t)(CB >> 32)));
}
__device__ __forceinline__ void wgmma_rl_56(float* d, uint32_t a0, uint32_t a1, uint32_t a2, uint32_t a3, uint64_t db, int sd) {
  asm volatile("{\n.reg .pred p;\nsetp.ne.b32 p, %33, 0;\n"
    "wgmma.mma_async.sync.aligned.m64n56k16.f32.bf16.bf16 {%0,%1,%2,%3,%4,%5,%6,%7,%8,%9,%10,%11,%12,%13,%14,%15,%16,%17,%18,%19,%20,%21,%22,%23,%24,%25,%26,%27}, {%28,%29,%30,%31}, %32, p, 1, 1, 1;\n}\n"
    : "+f"(d[0]),"+f"(d[1]),"+f"(d[2]),"+f"(d[3]),"+f"(d[4]),"+f"(d[5]),"+f"(d[6]),"+f"(d[7]),"+f"(d[8]),"+f"(d[9]),"+f"(d[10]),"+f"(d[11]),"+f"(d[12]),"+f"(d[13]),"+f"(d[14]),"+f"(d[15]),"+f"(d[16]),"+f"(d[17]),"+f"(d[18]),"+f"(d[19]),"+f"(d[20]),"+f"(d[21]),"+f"(d[22]),"+f"(d[23]),"+f"(d[24]),"+f"(d[25]),"+f"(d[26]),"+f"(d[27])
    : "r"(a0), "r"(a1), "r"(a2), "r"(a3), "l"(db), "r"(sd));
}
template<uint64_t CA, uint64_t CB> __device__ __forceinline__ void wgmma_ss_56(float* d, uint32_t da, uint32_t db, int sd) {
  asm volatile("{\n.reg .pred p;\n.reg .b64 a, b;\nsetp.ne.b32 p, %30, 0;\nmov.b64 a, {%28, %31};\nmov.b64 b, {%29, %32};\n"
    "wgmma.mma_async.sync.aligned.m64n56k16.f32.bf16.bf16 {%0,%1,%2,%3,%4,%5,%6,%7,%8,%9,%10,%11,%12,%13,%14,%15,%16,%17,%18,%19,%20,%21,%22,%23,%24,%25,%26,%27}, a, b, p, 1, 1, 0, 1;\n}\n"
    : "+f"(d[0]),"+f"(d[1]),"+f"(d[2]),"+f"(d[3]),"+f"(d[4]),"+f"(d[5]),"+f"(d[6]),"+f"(d[7]),"+f"(d[8]),"+f"(d[9]),"+f"(d[10]),"+f"(d[11]),"+f"(d[12]),"+f"(d[13]),"+f"(d[14]),"+f"(d[15]),"+f"(d[16]),"+f"(d[17]),"+f"(d[18]),"+f"(d[19]),"+f"(d[20]),"+f"(d[21]),"+f"(d[22]),"+f"(d[23]),"+f"(d[24]),"+f"(d[25]),"+f"(d[26]),"+f"(d[27])
    : "r"(da), "r"(db), "r"(sd), "n"((uint32_t)(CA >> 32)), "n"((uint32_t)(CB >> 32)));
}
__device__ __forceinline__ void wgmma_rl_256(float* d, uint32_t a0, uint32_t a1, uint32_t a2, uint32_t a3, uint64_t db, int sd) {
  asm volatile("{\n.reg .pred p;\nsetp.ne.b32 p, %133, 0;\n"
    "wgmma.mma_async.sync.aligned.m64n256k16.f32.bf16.bf16 {%0,%1,%2,%3,%4,%5,%6,%7,%8,%9,%10,%11,%12,%13,%14,%15,%16,%17,%18,%19,%20,%21,%22,%23,%24,%25,%26,%27,%28,%29,%30,%31,%32,%33,%34,%35,%36,%37,%38,%39,%40,%41,%42,%43,%44,%45,%46,%47,%48,%49,%50,%51,%52,%53,%54,%55,%56,%57,%58,%59,%60,%61,%62,%63,%64,%65,%66,%67,%68,%69,%70,%71,%72,%73,%74,%75,%76,%77,%78,%79,%80,%81,%82,%83,%84,%85,%86,%87,%88,%89,%90,%91,%92,%93,%94,%95,%96,%97,%98,%99,%100,%101,%102,%103,%104,%105,%106,%107,%108,%109,%110,%111,%112,%113,%114,%115,%116,%117,%118,%119,%120,%121,%122,%123,%124,%125,%126,%127}, {%128,%129,%130,%131}, %132, p, 1, 1, 1;\n}\n"
    : "+f"(d[0]),"+f"(d[1]),"+f"(d[2]),"+f"(d[3]),"+f"(d[4]),"+f"(d[5]),"+f"(d[6]),"+f"(d[7]),"+f"(d[8]),"+f"(d[9]),"+f"(d[10]),"+f"(d[11]),"+f"(d[12]),"+f"(d[13]),"+f"(d[14]),"+f"(d[15]),"+f"(d[16]),"+f"(d[17]),"+f"(d[18]),"+f"(d[19]),"+f"(d[20]),"+f"(d[21]),"+f"(d[22]),"+f"(d[23]),"+f"(d[24]),"+f"(d[25]),"+f"(d[26]),"+f"(d[27]),"+f"(d[28]),"+f"(d[29]),"+f"(d[30]),"+f"(d[31]),"+f"(d[32]),"+f"(d[33]),"+f"(d[34]),"+f"(d[35]),"+f"(d[36]),"+f"(d[37]),"+f"(d[38]),"+f"(d[39]),"+f"(d[40]),"+f"(d[41]),"+f"(d[42]),"+f"(d[43]),"+f"(d[44]),"+f"(d[45]),"+f"(d[46]),"+f"(d[47]),"+f"(d[48]),"+f"(d[49]),"+f"(d[50]),"+f"(d[51]),"+f"(d[52]),"+f"(d[53]),"+f"(d[54]),"+f"(d[55]),"+f"(d[56]),"+f"(d[57]),"+f"(d[58]),"+f"(d[59]),"+f"(d[60]),"+f"(d[61]),"+f"(d[62]),"+f"(d[63]),"+f"(d[64]),"+f"(d[65]),"+f"(d[66]),"+f"(d[67]),"+f"(d[68]),"+f"(d[69]),"+f"(d[70]),"+f"(d[71]),"+f"(d[72]),"+f"(d[73]),"+f"(d[74]),"+f"(d[75]),"+f"(d[76]),"+f"(d[77]),"+f"(d[78]),"+f"(d[79]),"+f"(d[80]),"+f"(d[81]),"+f"(d[82]),"+f"(d[83]),"+f"(d[84]),"+f"(d[85]),"+f"(d[86]),"+f"(d[87]),"+f"(d[88]),"+f"(d[89]),"+f"(d[90]),"+f"(d[91]),"+f"(d[92]),"+f"(d[93]),"+f"(d[94]),"+f"(d[95]),"+f"(d[96]),"+f"(d[97]),"+f"(d[98]),"+f"(d[99]),"+f"(d[100]),"+f"(d[101]),"+f"(d[102]),"+f"(d[103]),"+f"(d[104]),"+f"(d[105]),"+f"(d[106]),"+f"(d[107]),"+f"(d[108]),"+f"(d[109]),"+f"(d[110]),"+f"(d[111]),"+f"(d[112]),"+f"(d[113]),"+f"(d[114]),"+f"(d[115]),"+f"(d[116]),"+f"(d[117]),"+f"(d[118]),"+f"(d[119]),"+f"(d[120]),"+f"(d[121]),"+f"(d[122]),"+f"(d[123]),"+f"(d[124]),"+f"(d[125]),"+f"(d[126]),"+f"(d[127])
    : "r"(a0), "r"(a1), "r"(a2), "r"(a3), "l"(db), "r"(sd));
}
template<uint64_t CA, uint64_t CB> __device__ __forceinline__ void wgmma_ss_128(float* d, uint32_t da, uint32_t db, int sd) {
  asm volatile("{\n.reg .pred p;\n.reg .b64 a, b;\nsetp.ne.b32 p, %66, 0;\nmov.b64 a, {%64, %67};\nmov.b64 b, {%65, %68};\n"
    "wgmma.mma_async.sync.aligned.m64n128k16.f32.bf16.bf16 {%0,%1,%2,%3,%4,%5,%6,%7,%8,%9,%10,%11,%12,%13,%14,%15,%16,%17,%18,%19,%20,%21,%22,%23,%24,%25,%26,%27,%28,%29,%30,%31,%32,%33,%34,%35,%36,%37,%38,%39,%40,%41,%42,%43,%44,%45,%46,%47,%48,%49,%50,%51,%52,%53,%54,%55,%56,%57,%58,%59,%60,%61,%62,%63}, a, b, p, 1, 1, 0, 1;\n}\n"
    : "+f"(d[0]),"+f"(d[1]),"+f"(d[2]),"+f"(d[3]),"+f"(d[4]),"+f"(d[5]),"+f"(d[6]),"+f"(d[7]),"+f"(d[8]),"+f"(d[9]),"+f"(d[10]),"+f"(d[11]),"+f"(d[12]),"+f"(d[13]),"+f"(d[14]),"+f"(d[15]),"+f"(d[16]),"+f"(d[17]),"+f"(d[18]),"+f"(d[19]),"+f"(d[20]),"+f"(d[21]),"+f"(d[22]),"+f"(d[23]),"+f"(d[24]),"+f"(d[25]),"+f"(d[26]),"+f"(d[27]),"+f"(d[28]),"+f"(d[29]),"+f"(d[30]),"+f"(d[31]),"+f"(d[32]),"+f"(d[33]),"+f"(d[34]),"+f"(d[35]),"+f"(d[36]),"+f"(d[37]),"+f"(d[38]),"+f"(d[39]),"+f"(d[40]),"+f"(d[41]),"+f"(d[42]),"+f"(d[43]),"+f"(d[44]),"+f"(d[45]),"+f"(d[46]),"+f"(d[47]),"+f"(d[48]),"+f"(d[49]),"+f"(d[50]),"+f"(d[51]),"+f"(d[52]),"+f"(d[53]),"+f"(d[54]),"+f"(d[55]),"+f"(d[56]),"+f"(d[57]),"+f"(d[58]),"+f"(d[59]),"+f"(d[60]),"+f"(d[61]),"+f"(d[62]),"+f"(d[63])
    : "r"(da), "r"(db), "r"(sd), "n"((uint32_t)(CA >> 32)), "n"((uint32_t)(CB >> 32)));
}
template<uint64_t CA, uint64_t CB> __device__ __forceinline__ void wgmma_ss_64(float* d, uint32_t da, uint32_t db, int sd) {
  asm volatile("{\n.reg .pred p;\n.reg .b64 a, b;\nsetp.ne.b32 p, %34, 0;\nmov.b64 a, {%32, %35};\nmov.b64 b, {%33, %36};\n"
    "wgmma.mma_async.sync.aligned.m64n64k16.f32.bf16.bf16 {%0,%1,%2,%3,%4,%5,%6,%7,%8,%9,%10,%11,%12,%13,%14,%15,%16,%17,%18,%19,%20,%21,%22,%23,%24,%25,%26,%27,%28,%29,%30,%31}, a, b, p, 1, 1, 0, 1;\n}\n"
    : "+f"(d[0]),"+f"(d[1]),"+f"(d[2]),"+f"(d[3]),"+f"(d[4]),"+f"(d[5]),"+f"(d[6]),"+f"(d[7]),"+f"(d[8]),"+f"(d[9]),"+f"(d[10]),"+f"(d[11]),"+f"(d[12]),"+f"(d[13]),"+f"(d[14]),"+f"(d[15]),"+f"(d[16]),"+f"(d[17]),"+f"(d[18]),"+f"(d[19]),"+f"(d[20]),"+f"(d[21]),"+f"(d[22]),"+f"(d[23]),"+f"(d[24]),"+f"(d[25]),"+f"(d[26]),"+f"(d[27]),"+f"(d[28]),"+f"(d[29]),"+f"(d[30]),"+f"(d[31])
    : "r"(da), "r"(db), "r"(sd), "n"((uint32_t)(CA >> 32)), "n"((uint32_t)(CB >> 32)));
}
template<uint64_t CA, uint64_t CB> __device__ __forceinline__ void wgmma_ss_112(float* d, uint32_t da, uint32_t db, int sd) {
  asm volatile("{\n.reg .pred p;\n.reg .b64 a, b;\nsetp.ne.b32 p, %58, 0;\nmov.b64 a, {%56, %59};\nmov.b64 b, {%57, %60};\n"
    "wgmma.mma_async.sync.aligned.m64n112k16.f32.bf16.bf16 {%0,%1,%2,%3,%4,%5,%6,%7,%8,%9,%10,%11,%12,%13,%14,%15,%16,%17,%18,%19,%20,%21,%22,%23,%24,%25,%26,%27,%28,%29,%30,%31,%32,%33,%34,%35,%36,%37,%38,%39,%40,%41,%42,%43,%44,%45,%46,%47,%48,%49,%50,%51,%52,%53,%54,%55}, a, b, p, 1, 1, 0, 1;\n}\n"
    : "+f"(d[0]),"+f"(d[1]),"+f"(d[2]),"+f"(d[3]),"+f"(d[4]),"+f"(d[5]),"+f"(d[6]),"+f"(d[7]),"+f"(d[8]),"+f"(d[9]),"+f"(d[10]),"+f"(d[11]),"+f"(d[12]),"+f"(d[13]),"+f"(d[14]),"+f"(d[15]),"+f"(d[16]),"+f"(d[17]),"+f"(d[18]),"+f"(d[19]),"+f"(d[20]),"+f"(d[21]),"+f"(d[22]),"+f"(d[23]),"+f"(d[24]),"+f"(d[25]),"+f"(d[26]),"+f"(d[27]),"+f"(d[28]),"+f"(d[29]),"+f"(d[30]),"+f"(d[31]),"+f"(d[32]),"+f"(d[33]),"+f"(d[34]),"+f"(d[35]),"+f"(d[36]),"+f"(d[37]),"+f"(d[38]),"+f"(d[39]),"+f"(d[40]),"+f"(d[41]),"+f"(d[42]),"+f"(d[43]),"+f"(d[44]),"+f"(d[45]),"+f"(d[46]),"+f"(d[47]),"+f"(d[48]),"+f"(d[49]),"+f"(d[50]),"+f"(d[51]),"+f"(d[52]),"+f"(d[53]),"+f"(d[54]),"+f"(d[55])
    : "r"(da), "r"(db), "r"(sd), "n"((uint32_t)(CA >> 32)), "n"((uint32_t)(CB >> 32)));
}
__device__ __forceinline__ void wgmma_rl_112(float* d, uint32_t a0, uint32_t a1, uint32_t a2, uint32_t a3, uint64_t db, int sd) {
  asm volatile("{\n.reg .pred p;\nsetp.ne.b32 p, %61, 0;\n"
    "wgmma.mma_async.sync.aligned.m64n112k16.f32.bf16.bf16 {%0,%1,%2,%3,%4,%5,%6,%7,%8,%9,%10,%11,%12,%13,%14,%15,%16,%17,%18,%19,%20,%21,%22,%23,%24,%25,%26,%27,%28,%29,%30,%31,%32,%33,%34,%35,%36,%37,%38,%39,%40,%41,%42,%43,%44,%45,%46,%47,%48,%49,%50,%51,%52,%53,%54,%55}, {%56,%57,%58,%59}, %60, p, 1, 1, 1;\n}\n"
    : "+f"(d[0]),"+f"(d[1]),"+f"(d[2]),"+f"(d[3]),"+f"(d[4]),"+f"(d[5]),"+f"(d[6]),"+f"(d[7]),"+f"(d[8]),"+f"(d[9]),"+f"(d[10]),"+f"(d[11]),"+f"(d[12]),"+f"(d[13]),"+f"(d[14]),"+f"(d[15]),"+f"(d[16]),"+f"(d[17]),"+f"(d[18]),"+f"(d[19]),"+f"(d[20]),"+f"(d[21]),"+f"(d[22]),"+f"(d[23]),"+f"(d[24]),"+f"(d[25]),"+f"(d[26]),"+f"(d[27]),"+f"(d[28]),"+f"(d[29]),"+f"(d[30]),"+f"(d[31]),"+f"(d[32]),"+f"(d[33]),"+f"(d[34]),"+f"(d[35]),"+f"(d[36]),"+f"(d[37]),"+f"(d[38]),"+f"(d[39]),"+f"(d[40]),"+f"(d[41]),"+f"(d[42]),"+f"(d[43]),"+f"(d[44]),"+f"(d[45]),"+f"(d[46]),"+f"(d[47]),"+f"(d[48]),"+f"(d[49]),"+f"(d[50]),"+f"(d[51]),"+f"(d[52]),"+f"(d[53]),"+f"(d[54]),"+f"(d[55])
    : "r"(a0), "r"(a1), "r"(a2), "r"(a3), "l"(db), "r"(sd));
}

constexpr int DM = 448;
constexpr int NCTA = 128;
#define WIN 5
#define GEMV_AT 1
#define NPRE 14
#define VPRE 3
constexpr int SPIN_LIMIT = 1 << 22;

constexpr uint32_t OFF_X = 0, OFF_Y = 114688, OFF_MISC = 229376, SMEM_BYTES = 232448;
constexpr uint32_t Y_VR = 0, Y_K = 28672, Y_KOWN = 57344, Y_VOWN = 71680, Y_Q = 86016;
constexpr uint32_t HALF = 57344;
constexpr uint32_t X_STAT = 49152;
constexpr uint32_t OUT_STAGE = 4 * 16384;
constexpr uint32_t M_BAR = OFF_MISC;
constexpr uint32_t M_ST = OFF_MISC + 512;
constexpr uint32_t M_G = OFF_MISC + 2304;
constexpr uint32_t M_EPOCH = OFF_MISC + 3040;
enum { B_XFULL = 0, B_FULLK = 7, B_FULLV = 8, B_FULLQ, B_KRFULL, B_VRFULL, B_WOFULL, B_XCH, B_MOD1 = 15, B_FULL = 16, B_WMFULL = 30,
       B_EMPTY = 32, B_PEER = 45, B_DUMMY,
       B_PUB = 47,
       B_XFREE = B_PUB + 4, B_GEMV,
       B_WMFREE = 56, B_HRDY, B_GFULL = B_HRDY + 3, B_DONE = 31 };

__device__ uint32_t g_ticket;
__device__ __align__(128) uint32_t g_mod[8 * 6 * DM];
__device__ __align__(128) uint32_t g_flag[144 * 192];
constexpr int RB_WORDS = 262144, RB_KV = 0, RB_O = 57344, RB_X1 = 86016, RB_H2 = 143360, RB_ST = 258048;
__device__ __align__(128) uint32_t g_act[17 * RB_WORDS];
__device__ __align__(128) uint32_t g_wd[56 * 4 * 1792];
#define PROFH(id)
#define PROFH1(id)
#define PROFC(id)

struct alignas(64) Params {
    CUtensorMap wm, wm2, om, xm, qkv, wo, ga, ua, gb, ub, gc, uc, dn;
    const bf16 *x, *c, *wqkv, *wmod, *wg, *wu, *wd, *wop;
    bf16* out;
    uint32_t* actb;
    uint32_t zero;
};

__device__ __forceinline__ void mbar_init(uint32_t bar, int cnt) { asm volatile("mbarrier.init.shared::cta.b64 [%0], %1;" ::"r"(bar), "r"(cnt) : "memory"); }
__device__ __forceinline__ void mbar_arrive(uint32_t bar) { asm volatile("mbarrier.arrive.shared::cta.b64 _, [%0];" ::"r"(bar) : "memory"); }
__device__ __forceinline__ void mbar_wait(uint32_t bar, uint32_t parity) {
    uint32_t ok; int n = 0;
    do {
        asm volatile("{\n.reg .pred p;\nmbarrier.try_wait.parity.shared::cta.b64 p, [%1], %2;\nselp.u32 %0, 1, 0, p;\n}" : "=r"(ok) : "r"(bar), "r"(parity) : "memory");
        if (++n > SPIN_LIMIT) __trap();
    } while (!ok);
}
__device__ __forceinline__ void mbar_wait_c(uint32_t bar, uint32_t parity) {
    asm volatile("{\n.reg .pred p;\nWL:\nmbarrier.try_wait.parity.shared::cta.b64 p, [%0], %1, 0x989680;\n@!p bra WL;\n}" ::"r"(bar), "r"(parity) : "memory");
}
__device__ __forceinline__ void mbar_wait_cluster(uint32_t bar, uint32_t parity) {
    asm volatile("{\n.reg .pred p;\nWL:\nmbarrier.try_wait.parity.acquire.cluster.shared::cta.b64 p, [%0], %1, 0x989680;\n@!p bra WL;\n}" ::"r"(bar), "r"(parity) : "memory");
}
__device__ __forceinline__ void warp_arrive(uint32_t bar) {
    __syncwarp();
    asm volatile("{\n.reg .pred p;\nelect.sync _|p, 0xffffffff;\n@p mbarrier.arrive.shared::cta.b64 _, [%0];\n}" ::"r"(bar) : "memory");
}
__device__ __forceinline__ int opaque(int v) { return __shfl_sync(~0u, v, 0); }
__device__ __forceinline__ int fresh_tid() { int v; asm volatile("mov.u32 %0, %%tid.x;" : "=r"(v)); return v; }
__device__ __forceinline__ void bar_sync(int id, int n) { asm volatile("bar.sync %0, %1;" ::"r"(id), "r"(n) : "memory"); }
__device__ __forceinline__ void bar_arrive(int id, int n) { asm volatile("bar.arrive %0, %1;" ::"r"(id), "r"(n) : "memory"); }
__device__ __forceinline__ void fence_async_smem() { asm volatile("fence.proxy.async.shared::cta;" ::: "memory"); }
__device__ __forceinline__ void fence_async_global() { asm volatile("fence.proxy.async.global;" ::: "memory"); }
__device__ __forceinline__ void fence_gpu() { asm volatile("fence.release.gpu;" ::: "memory"); }
__device__ __forceinline__ void expect_e(uint32_t bar, uint32_t bytes) {
    asm volatile("{\n.reg .pred p;\nelect.sync _|p, 0xffffffff;\n@p mbarrier.arrive.expect_tx.shared::cta.b64 _, [%0], %1;\n}" ::"r"(bar), "r"(bytes) : "memory");
}
__device__ __forceinline__ void tma3_e(uint32_t dst, const CUtensorMap* m, int c0, int c1, int c2, uint32_t bar) {
    asm volatile("{\n.reg .pred p;\nelect.sync _|p, 0xffffffff;\n@p cp.async.bulk.tensor.3d.shared::cluster.global.mbarrier::complete_tx::bytes [%0], [%1, {%3, %4, %5}], [%2];\n}"
                 ::"r"(dst), "l"(m), "r"(bar), "r"(c0), "r"(c1), "r"(c2) : "memory");
}
__device__ __forceinline__ void bulk_e(uint32_t dst, const void* src, uint32_t bytes, uint32_t bar) {
    asm volatile("{\n.reg .pred p;\nelect.sync _|p, 0xffffffff;\n@p cp.async.bulk.shared::cluster.global.mbarrier::complete_tx::bytes [%0], [%1], %2, [%3];\n}"
                 ::"r"(dst), "l"(src), "r"(bytes), "r"(bar) : "memory");
}
__device__ __forceinline__ void init_e(uint32_t bar, int cnt) {
    asm volatile("{\n.reg .pred p;\nelect.sync _|p, 0xffffffff;\n@p mbarrier.init.shared::cta.b64 [%0], %1;\n}" ::"r"(bar), "r"(cnt) : "memory");
}
__device__ __forceinline__ void l2_prefetch_e(const void* src, uint32_t bytes) {
    asm volatile("{\n.reg .pred p;\nelect.sync _|p, 0xffffffff;\n@p cp.async.bulk.prefetch.L2.global [%0], %1;\n}" ::"l"(src), "r"(bytes) : "memory");
}
__device__ __forceinline__ uint32_t ld_relaxed(const uint32_t* p) { uint32_t v; asm volatile("ld.relaxed.gpu.global.u32 %0, [%1];" : "=r"(v) : "l"(p) : "memory"); return v; }
__device__ __forceinline__ void st_relaxed(uint32_t* p, uint32_t v) { asm volatile("st.relaxed.gpu.global.u32 [%0], %1;" ::"l"(p), "r"(v) : "memory"); }
__device__ __forceinline__ uint4 ld_relaxed4(const uint4* p) { uint4 v; asm volatile("ld.relaxed.gpu.global.v4.u32 {%0,%1,%2,%3}, [%4];" : "=r"(v.x), "=r"(v.y), "=r"(v.z), "=r"(v.w) : "l"(p) : "memory"); return v; }
__device__ __forceinline__ uint4 lds4(uint32_t a) { uint4 v; asm volatile("ld.shared.v4.u32 {%0,%1,%2,%3}, [%4];" : "=r"(v.x), "=r"(v.y), "=r"(v.z), "=r"(v.w) : "r"(a) : "memory"); return v; }
__device__ __forceinline__ float2 lds2f(uint32_t a) { float2 v; asm volatile("ld.shared.v2.f32 {%0,%1}, [%2];" : "=f"(v.x), "=f"(v.y) : "r"(a) : "memory"); return v; }
__device__ __forceinline__ uint32_t lds1(uint32_t a) { uint32_t v; asm volatile("ld.shared.u32 %0, [%1];" : "=r"(v) : "r"(a) : "memory"); return v; }
__device__ __forceinline__ void sts4(uint32_t a, uint4 v) { asm volatile("st.shared.v4.u32 [%0], {%1,%2,%3,%4};" ::"r"(a), "r"(v.x), "r"(v.y), "r"(v.z), "r"(v.w) : "memory"); }
__device__ __forceinline__ void sts1(uint32_t a, uint32_t v) { asm volatile("st.shared.u32 [%0], %1;" ::"r"(a), "r"(v) : "memory"); }
__device__ __forceinline__ void stsm4(uint32_t a, uint32_t r0, uint32_t r1, uint32_t r2, uint32_t r3) {
    asm volatile("stmatrix.sync.aligned.m8n8.x4.shared.b16 [%0], {%1,%2,%3,%4};" ::"r"(a), "r"(r0), "r"(r1), "r"(r2), "r"(r3));
}
__device__ __forceinline__ uint32_t pack2(float lo, float hi) { uint32_t r; asm("cvt.rn.bf16x2.f32 %0, %1, %2;" : "=r"(r) : "f"(hi), "f"(lo)); return r; }
__device__ __forceinline__ uint32_t pack2_relu(float lo, float hi) { uint32_t r; asm("cvt.rn.relu.bf16x2.f32 %0, %1, %2;" : "=r"(r) : "f"(hi), "f"(lo)); return r; }
__device__ __forceinline__ uint32_t hfma2(uint32_t a, uint32_t b, uint32_t c) { uint32_t r; asm("fma.rn.bf16x2 %0, %1, %2, %3;" : "=r"(r) : "r"(a), "r"(b), "r"(c)); return r; }
__device__ __forceinline__ uint32_t hmul2(uint32_t a, uint32_t b) { uint32_t r; asm("mul.rn.bf16x2 %0, %1, %2;" : "=r"(r) : "r"(a), "r"(b)); return r; }
__device__ __forceinline__ float bf_lo(uint32_t v) { return __uint_as_float(v << 16); }
__device__ __forceinline__ float bf_hi(uint32_t v) { return __uint_as_float(v & 0xFFFF0000u); }
__device__ __forceinline__ float bf_round(float v) { return bf_lo(pack2(v, 0.f)); }
__device__ __forceinline__ float ex2(float x) { float r; asm("ex2.approx.ftz.f32 %0, %1;" : "=f"(r) : "f"(x)); return r; }
__device__ __forceinline__ void mma16816(float* d, uint32_t a0, uint32_t a1, uint32_t a2, uint32_t a3, uint32_t b0, uint32_t b1) {
    asm("mma.sync.aligned.m16n8k16.row.col.f32.bf16.bf16.f32 {%0,%1,%2,%3}, {%4,%5,%6,%7}, {%8,%9}, {%0,%1,%2,%3};"
        : "+f"(d[0]), "+f"(d[1]), "+f"(d[2]), "+f"(d[3]) : "r"(a0), "r"(a1), "r"(a2), "r"(a3), "r"(b0), "r"(b1));
}
__device__ __forceinline__ void mma1688(float* d, uint32_t a0, uint32_t a1, uint32_t b0) {
    asm("mma.sync.aligned.m16n8k8.row.col.f32.bf16.bf16.f32 {%0,%1,%2,%3}, {%4,%5}, {%6}, {%0,%1,%2,%3};"
        : "+f"(d[0]), "+f"(d[1]), "+f"(d[2]), "+f"(d[3]) : "r"(a0), "r"(a1), "r"(b0));
}
__device__ __forceinline__ void ldsm4(uint32_t a, uint32_t* r) {
    asm volatile("ldmatrix.sync.aligned.m8n8.x4.shared.b16 {%0,%1,%2,%3}, [%4];" : "=r"(r[0]), "=r"(r[1]), "=r"(r[2]), "=r"(r[3]) : "r"(a));
}
__device__ __forceinline__ void ldsm4t(uint32_t a, uint32_t* r) {
    asm volatile("ldmatrix.sync.aligned.m8n8.x4.trans.shared.b16 {%0,%1,%2,%3}, [%4];" : "=r"(r[0]), "=r"(r[1]), "=r"(r[2]), "=r"(r[3]) : "r"(a));
}
__device__ __forceinline__ uint32_t nz(uint32_t v) { uint32_t r; asm("max.u32 %0, %1, 1;" : "=r"(r) : "r"(v)); return r; }
__device__ __forceinline__ float rcp(float x) { float r; asm("rcp.approx.ftz.f32 %0, %1;" : "=f"(r) : "f"(x)); return r; }
__device__ __forceinline__ uint2 ld_relaxed2(const void* p) { uint2 v; asm volatile("ld.relaxed.gpu.global.v2.u32 {%0,%1}, [%2];" : "=r"(v.x), "=r"(v.y) : "l"(p) : "memory"); return v; }
__host__ __device__ constexpr uint64_t dconst(uint32_t lbo, uint32_t sbo, uint32_t swz) {
    return ((uint64_t)(lbo >> 4) << 16) | ((uint64_t)(sbo >> 4) << 32) | ((uint64_t)swz << 62);
}
__device__ __forceinline__ uint32_t mkdesc(uint32_t addr, uint64_t c) { return (uint32_t)c | ((addr & 0x3FFFF) >> 4); }
#define WG_FENCE() asm volatile("wgmma.fence.sync.aligned;" ::: "memory")
#define WG_COMMIT() asm volatile("wgmma.commit_group.sync.aligned;" ::: "memory")
#define WG_WAIT(n) asm volatile("wgmma.wait_group.sync.aligned %0;" ::"n"(n) : "memory")
template <int N> __device__ __forceinline__ void reg_fence(float* d) {
#pragma unroll
    for (int i = 0; i < N; i++) asm volatile("" : "+f"(d[i])::"memory");
}
template <int N> __device__ __forceinline__ void reg_def(float* d) {
#pragma unroll
    for (int i = 0; i < N; i++) asm volatile("" : "=f"(d[i]));
}
template <int N> __device__ __forceinline__ void reg_def(uint32_t* d) {
#pragma unroll
    for (int i = 0; i < N; i++) asm volatile("" : "=r"(d[i]));
}
__device__ __forceinline__ void wait_flags(const uint32_t* p, uint32_t target, uint32_t mask) {
    int n = 0;
    while (~__ballot_sync(~0u, ld_relaxed(p) == target) & mask) { if (++n > SPIN_LIMIT) __trap(); }
    asm volatile("fence.acquire.gpu;" ::: "memory");
}
__device__ __forceinline__ float silu_bf(uint32_t cbits) {
    const float c = __uint_as_float(cbits << 16);
    return bf_round(__fdividef(c, 1.f + fminf(ex2(-1.4426950408889634f * c), 1e30f)));
}
__device__ __forceinline__ void gemv_part(uint32_t wmbuf, int wp, int lane) {
    const uint32_t wa = wmbuf + wp * 512 + (8 * (lane >> 4) + (lane & 7)) * 32 + ((lane >> 3) & 1) * 16;
    float d[4] = {};
#pragma unroll
    for (int i = 0; i < 4; i++) {
        uint32_t A[4];
        const float2 v = lds2f(wmbuf + 28672 + (wp + 8 * i) * 32 + (lane & 3) * 8);
        ldsm4t(wa + (i < 3 || wp < 4 ? i : 0) * 4096, A);
        mma16816(d, A[0], A[1], A[2], A[3], __float_as_uint(v.x), __float_as_uint(v.y));
    }
    if ((lane & 3) == 0) {
        sts1(wmbuf + 29696 + (wp * 16 + (lane >> 2)) * 4, __float_as_uint(d[0]));
        sts1(wmbuf + 29696 + (wp * 16 + 8 + (lane >> 2)) * 4, __float_as_uint(d[2]));
    }
}
__device__ __forceinline__ uint32_t mod_word(float v, int col, uint32_t target) {
    v = bf_round(v);
    if ((col >= DM && col < 2 * DM) || (col >= 4 * DM && col < 5 * DM)) v += 1.f;
    return (pack2(v, 0.f) << 16) | (target & 0xFFFFu);
}
__device__ __forceinline__ const uint4* mod_src(int i, int r, int j, bool p2) {
    i = min(i, p2 ? 251 : 223);
    return (const uint4*)g_mod + (r & 7) * (6 * DM / 4) + (i < 224 ? (p2 ? 336 : 0) + i : (i < 238 ? 14 * j + i : 14 * j + i + 322));
}
__device__ __forceinline__ void mod_store(uint32_t sb, uint4 v, const uint4* src, int i) {
    const uint32_t tag = lds1(sb + M_EPOCH) + 1;
    while (__any_sync(~0u, (((v.x ^ tag) | (v.y ^ tag) | (v.z ^ tag) | (v.w ^ tag)) & 0xFFFFu) != 0u)) v = ld_relaxed4(src);
    if (i < 224) {
        const int isc = i >= 112, c4 = i - 112 * isc;
        const uint32_t a = sb + M_ST + (c4 >> 2) * 64 + (c4 & 1) * 32 + (c4 & 2) * 4 + (isc ? 0 : 4);
        sts1(a, __byte_perm(v.x, v.y, 0x7632));
        sts1(a + 16, __byte_perm(v.z, v.w, 0x7632));
    } else if (i < 252) {
        sts4(sb + M_G + (i - 224) * 16, make_uint4(v.x & 0xFFFF0000u, v.y & 0xFFFF0000u, v.z & 0xFFFF0000u, v.w & 0xFFFF0000u));
    }
}
__device__ __forceinline__ int pass_f(int fs, int ps) { return 224 * fs + ((fs & 1) ? (ps == 0 ? 96 : ps == 1 ? 32 : 0) : (ps == 0 ? 0 : ps == 1 ? 128 : 192)); }
__device__ __forceinline__ constexpr uint32_t slot_off(int l) { return l * 16384 + (l >= 10 ? 8192 : 0); }
constexpr uint64_t RING_ORDER = 0x6543C92B81A70ull;
constexpr uint32_t Y_XCH = 49152;
__device__ __forceinline__ constexpr int g1_slot(int s) { return s % 7; }
__device__ __noinline__ void x1_fix(const uint32_t* g, uint32_t sa, int s) {
#pragma unroll 1
    for (int k = 4 * s; k < 4 * s + 4;) {
        const uint4 v = ld_relaxed4((const uint4*)(g + k * 256));
        sts4(sa + k * 1024, v);
        k += 2 * __all_sync(~0u, min(min(v.x, v.y), min(v.z, v.w)) != 0u);
    }
    __syncwarp();
}
struct LnRow { uint32_t nm, hi, lo; };
__device__ __forceinline__ LnRow ln_coeffs(float mean, float msq) {
    const float var = bf_round(fmaxf(msq - mean * mean, 0.f));
    float sd;
    asm("sqrt.approx.f32 %0, %1;" : "=f"(sd) : "f"(bf_round(var + 1e-5f)));
    const float inv = rcp(bf_round(sd)), hi = bf_round(inv);
    LnRow c;
    c.nm = pack2(-bf_round(mean) * hi, -bf_round(mean) * hi);
    c.hi = pack2(hi, hi);
    c.lo = pack2(inv - hi, inv - hi);
    return c;
}
__device__ __forceinline__ uint32_t ln_norm(uint32_t x, const LnRow& c) {
    return hfma2(x, c.hi, c.nm);
}
__device__ __forceinline__ uint32_t ln_mod(uint32_t y, uint32_t sc, uint32_t sh) {
    return hfma2(y, sc, sh);
}

#define LOADW bulk_e(dst, g_wd + (size_t)((f >> 5) * 4 + nq) * 1792, 7168, bar);
template <int sec> __device__ __forceinline__ void ring_loader(const Params& p, uint32_t sb_, int r_, int j_, int lane) {
    const uint32_t sb = opaque(sb_);
    const int r = opaque(r_), j = opaque(j_), nq = j >> 1, fs = 4 * (j & 1) + nq;
    const int fa = pass_f(fs, 0), fb = pass_f(fs, 1), fc = pass_f(fs, 2);
    const uint32_t* h2src = (const uint32_t*)__shfl_sync(~0u, (unsigned long long)(p.actb + (size_t)r * RB_WORDS + RB_H2), 0);
    const CUtensorMap* gmap = (const CUtensorMap*)__shfl_sync(~0u, (unsigned long long)(&p.ga + sec), 0);
#define BAR(i) (sb + M_BAR + 8 * (i))
#define kh (j & 1)
            int sl = 0;
#pragma unroll 1
            for (int s = 0; s < 21; s++) {
                if (s == 7) { wait_flags(g_flag + (8 * r + j) * 192 + 96 + lane, lds1(sb + M_EPOCH) + 1, 0xFFFFu); fence_async_global(); }
                if (s >= 1 && s < 6) mbar_wait(BAR(B_FULL + s - 1), 0);
                mbar_wait(BAR(B_EMPTY + sl), s >= 7 && s < 14);
                expect_e(BAR(B_FULL + sl), 8192);
                tma3_e(sb + slot_off(sl) + sec * 8192, gmap + (s < 14 ? 0 : 2), 0, s < 14 ? 32 * s : 64 * sl, (s < 14 ? fa : fb) >> 6, BAR(B_FULL + sl));
                sl = sl == 6 ? 0 : sl + 1;
            }
#pragma unroll 1
            for (int s = 0; s < 7; s++) {
                const uint32_t bar = BAR(B_FULL + s);
                uint32_t dst = sb + slot_off(s) + sec * 4096;
                mbar_wait(BAR(B_EMPTY + s), 1);
                expect_e(bar, s < 3 ? 8192 : s > 3 ? 7168 : sec ? 4096 : 4096 + 7168);
                if (s < 4) tma3_e(dst, gmap + 4, 0, 128 * s, fc >> 5, bar);
                if (s < 3) tma3_e(dst + 8192, gmap + 4, 0, 128 * s + 64, fc >> 5, bar);
                else if (s > 3 || !sec) {
                    const int f = s == 3 ? fc : (s < 6 ? fa + 64 * (s - 4) : fb) + 32 * sec;
                    dst = sb + slot_off(s) + (s == 3 || sec ? 8192 : 0);
                    LOADW
                }
            }
            if (!sec) PROFH(3);
            if (sec) asm volatile("prefetch.tensormap [%0];" ::"l"(&p.om) : "memory");
            int e = 0;
#pragma unroll 1
            for (int grp = 0; grp < 9; grp++) {
                const int ps = grp >= 6 ? 2 : grp >= 3 ? 1 : 0;
                int sidx = grp - 3 * ps;
                if (sec && sidx == 0) { mbar_wait(BAR(B_HRDY + ps), 0); fence_async_global(); }
                sidx += sidx >= nq;
                int f = pass_f(4 * kh + sidx, ps);
#pragma unroll 1
                for (int k = 4 >> ps; k > 0; k--, e++, f += 32) {
                    sl = (RING_ORDER >> (4 * (e < 13 ? e : e - 13))) & 15;
                    const uint32_t dst = sb + slot_off(sl), bar = BAR(B_FULL + sl);
                    mbar_wait(BAR(B_EMPTY + sl), e >= 13);
                    if (e >= WIN) mbar_wait(BAR(B_FULL + ((RING_ORDER >> (4 * (e - WIN < 13 ? e - WIN : e - WIN - 13))) & 15)), e - WIN >= 13);
                    expect_e(bar, sec ? 8192 : 7168);
                    if (!sec) { LOADW }
                    else bulk_e(dst + 8192, h2src + f * 64, 8192, bar);
                }
            }
            if (!sec) PROFH(4);
}

#define PROF_PARAMS
#define PROF_ARGS
__device__ __noinline__ void helper_late(const Params& p, int r_, int j_, int warp_ PROF_PARAMS) {
    extern __shared__ __align__(1024) unsigned char smem[];
    const uint32_t sb = (uint32_t)__cvta_generic_to_shared(smem);
    const int r = opaque(r_), j = opaque(j_), warp = opaque(warp_), nq = j >> 1, b = 8 * r + j;
    uint32_t* const act = (uint32_t*)__shfl_sync(~0u, (unsigned long long)(p.actb + (size_t)r * RB_WORDS), 0);
    {
        const int lane = fresh_tid() & 31;
        const uint32_t target = lds1(sb + M_EPOCH) + 1;
        if (warp == 8) { expect_e(BAR(B_XCH), 7168); expect_e(BAR(B_XCH + 1), 7168); }
            if (warp == 9) {
#pragma unroll 1
                for (int kv = 0; kv < 2; kv++) {
                    mbar_wait(BAR(B_PUB + kv), 0);
                    wait_flags(g_flag + b * 192 + lane, target, (r >= 2 ? 6u : r == 1 ? 2u : 0u) << (8 * kv));
                    fence_async_global();
                    const uint32_t dst = sb + OFF_Y + (kv ? Y_VR : Y_K);
                    expect_e(BAR(B_KRFULL + kv), r >= 2 ? 28672 : r == 1 ? 14336 : 0);
                    if (r >= 2) bulk_e(dst, act - 2 * RB_WORDS + RB_KV + j * 7168 + kv * 3584, 14336, BAR(B_KRFULL + kv));
                    if (r >= 1) bulk_e(dst + 14336, act - RB_WORDS + RB_KV + j * 7168 + kv * 3584, 14336, BAR(B_KRFULL + kv));
                    if (kv == 0) { PROFH(8); }
                }
            } else if (warp == 8) {
                uint4 v[8];
                mbar_wait(BAR(B_WOFULL), 0);
#pragma unroll
                for (int k = 0; k < 8; k++) v[k] = ld_relaxed4(mod_src(lane + 32 * k, r, j, true));
#pragma unroll
                for (int k = 0; k < 8; k++) mod_store(sb, v[k], mod_src(lane + 32 * k, r, j, true), lane + 32 * k);
                warp_arrive(BAR(B_MOD1));
            } else if (warp == 11) {
                if (kh == 1 && r < 14) {
                    const uint32_t wmbuf = sb + OFF_X + HALF;
                    const int mcol = 2 * DM + 32 * (4 * r + nq);
                    mbar_wait(BAR(B_XFREE), 0);
                    tma3_e(wmbuf, &p.wm2, mcol, 0, 0, BAR(B_WMFULL));
                    tma3_e(wmbuf + 14336, &p.wm2, mcol, 224, 0, BAR(B_WMFULL));
#pragma unroll 1
                    for (int wd = lane; wd < 224; wd += 32) {
                        const uint32_t cb = __ldg((const uint32_t*)p.c + wd);
                        sts1(wmbuf + 28672 + (wd >> 3) * 32 + (wd & 3) * 8 + (wd & 4), pack2(silu_bf(cb & 0xFFFFu), silu_bf(cb >> 16)));
                    }
                    __syncwarp();
                    mbar_wait(BAR(B_WMFULL), 0);
                    const uint32_t wa = wmbuf + (8 * (lane >> 4) + (lane & 7)) * 64 + ((lane >> 3) & 1) * 16;
                    float d[2][4] = {};
#pragma unroll 4
                    for (int ks = 0; ks < 28; ks++) {
                        uint32_t A[8];
                        ldsm4t(wa + ks * 1024, A); ldsm4t(wa + ks * 1024 + 32, A + 4);
                        const float2 v = lds2f(wmbuf + 28672 + ks * 32 + (lane & 3) * 8);
                        mma16816(d[0], A[0], A[1], A[2], A[3], __float_as_uint(v.x), __float_as_uint(v.y));
                        mma16816(d[1], A[4], A[5], A[6], A[7], __float_as_uint(v.x), __float_as_uint(v.y));
                    }
                    const int q = lane & 3, col = mcol + 8 * q + (lane >> 2);
                    const uint32_t word = mod_word(q == 0 ? d[0][0] : q == 1 ? d[0][2] : q == 2 ? d[1][0] : d[1][2], col, target);
#pragma unroll
                    for (int i = 0; i < 8; i++) st_relaxed(g_mod + i * 6 * DM + col, word);
                }
                warp_arrive(BAR(B_WMFREE));
                mbar_wait(BAR(B_VRFULL), 0);
                l2_prefetch_e((const char*)p.wg + (size_t)b * 12544, 12544);
                l2_prefetch_e((const char*)p.wu + (size_t)b * 12544, 12544);
#pragma unroll 1
                for (int k = 0; k < (r < 12 ? 2 : 1); k++) {
                    const int u = 28 * kh + r + 16 * k;
                    expect_e(BAR(B_XFULL + k), 7168);
                    tma3_e(sb + OFF_Y + 102400, &p.dn, 0, 32 * u, 7 * j, BAR(B_XFULL + k));
                    tma3_e(sb + OFF_Y + 102400 + 3584, &p.dn, 0, 32 * u, 7 * (j ^ 1), BAR(B_XFULL + k));
                    mbar_wait(BAR(B_XFULL + k), 1);
                    asm volatile("{\n.reg .pred p;\nelect.sync _|p, 0xffffffff;\n@p cp.async.bulk.global.shared::cta.bulk_group [%0], [%1], 7168;\n"
                                 "cp.async.bulk.commit_group;\ncp.async.bulk.wait_group 0;\n}" ::"l"(g_wd + (size_t)(u * 4 + nq) * 1792), "r"(sb + OFF_Y + 102400) : "memory");
                    __syncwarp();
                }
                warp_arrive(BAR(B_FULLK));
                fence_gpu();
                if (lane < 16) st_relaxed(g_flag + (8 * lane + j) * 192 + 96 + r, target);
            }
        if (warp == 8 || warp == 11) {
            const int sec = warp == 11;
            if (sec) ring_loader<1>(p, sb, r, j, lane); else ring_loader<0>(p, sb, r, j, lane);
            mbar_wait(BAR(B_DONE), 0);
        } else if (warp == 9) {
#pragma unroll
            for (int ev = 0; ev < 4; ev++) { expect_e(BAR(B_GFULL + ev), ev < 2 ? HALF / 2 : 16384); expect_e(BAR(B_XFULL + 2 + ev), ev < 2 ? HALF / 2 : HALF - 16384); }
            mbar_wait(BAR(B_PUB + 2), 0);
            expect_e(BAR(B_FULLV), 4096); expect_e(BAR(B_FULLQ), 4096);
            const int par = (target - 1) & 1;
#pragma unroll 1
            for (int ev = 0; ev < 4; ev++) {
                if (ev == 1) { mbar_wait(BAR(B_FULLK), 1); mbar_wait(BAR(B_PUB + 3), 0); }
                const int tile = (ev & 1) + (ev >> 1) * par * 2;
                const uint32_t dst = sb + (ev == 0 ? OFF_X : OFF_Y + (ev & 1) * HALF), first = ev < 2 ? HALF / 2 : 16384;
                const char* src = (const char*)(act + RB_O + ((ev >> 1) * 2 + tile) * 14336);
                wait_flags(g_flag + b * 192 + (ev < 2 ? 32 : 64 + 32 * ev) + lane, target, ev < 2 ? 0xFFu << (8 * ev) : ~0u);
                fence_async_global();
                if (ev >= 2) bulk_e(sb + OFF_X + X_STAT + (ev & 1) * 49152, act + RB_ST + tile * 1024, 4096, BAR(B_FULLV + (ev & 1)));
                bulk_e(dst, src, first, BAR(B_GFULL + ev));
                bulk_e(dst + first, src + first, HALF - first, BAR(B_XFULL + 2 + ev));
                if (ev) PROFH(4 + ev);
            }
            mbar_wait(BAR(B_XFULL + 5), 1);
#pragma unroll 1
            for (int hf = 0; hf < 2; hf++) {
                const int tile = (par ^ 1) * 2 + hf;
                uint4* xz = (uint4*)(act + RB_X1 + tile * 14336 + j * 1792) + lane;
#pragma unroll
                for (int i = 0; i < 14; i++) xz[i * 32] = make_uint4(0, 0, 0, 0);
                ((uint4*)(act + RB_ST + (tile * 8 + j) * 128))[lane] = make_uint4(0, 0, 0, 0);
            }
#pragma unroll 1
            for (int ps = 0; ps < 3; ps++) {
                mbar_wait(BAR(B_PUB + 6 + ps), 0);
                if (ps == 1) {
                    fence_gpu();
                    if (lane < 8) st_relaxed(g_flag + (8 * r + lane) * 192 + 72 + j, target);
                }
                wait_flags(g_flag + b * 192 + 64 + lane, target, (0x55u << kh) << (8 * ps));
                warp_arrive(BAR(B_HRDY + ps));
                PROFH(9 + ps);
            }
        } else {
#pragma unroll 1
            for (int k = 0; k < 9; k++) {
                if (k == 4 || k == 5 || k == 7) continue;
                uint32_t* fp = k < 2 ? g_flag + (b + 8 * lane) * 192 + k * 8 + lane : g_flag + (8 * r + lane) * 192 + 16 + k * 8 + j;
                mbar_wait(BAR(B_PUB + k), 0);
                fence_gpu();
                if (k < 2 ? (lane == 1 || lane == 2) : lane < 8) st_relaxed(fp, target);
                if (k >= 3 && k <= 5) PROFH(k - 3);
            }
        }
    }
}

__global__ void __cluster_dims__(2, 1, 1) __launch_bounds__(384, 1) fused_block_kernel(const __grid_constant__ Params p) {
    extern __shared__ __align__(1024) unsigned char smem[];
    const uint32_t sb = (uint32_t)__cvta_generic_to_shared(smem);
    const int tid = threadIdx.x, lane = tid & 31, warp = __shfl_sync(~0u, tid >> 5, 0);
    const int m = blockIdx.x >> 1;
    int r, nq;
    if (m < 4) { r = 15; nq = m; }
    else if (m < 36) { r = (m - 4) & 7; nq = (m - 4) >> 3; }
    else { nq = (m - 36) / 7; r = m - 28 - 7 * nq; }
    const int j = opaque(2 * nq + (blockIdx.x & 1)), b = 8 * r + j, fs = 4 * kh + nq;
#define act (p.actb + (size_t)r * RB_WORDS)
    uint32_t cw = 0;
    if (tid < 224) cw = __ldg((const uint32_t*)p.c + tid);
    if (tid == 255) cw = atomicAdd(&g_ticket, 1u);
    if (warp == 10 && blockIdx.x < 112) {
#pragma unroll
        for (int i = 0; i < 4; i++) l2_prefetch_e(p.wmod + (size_t)(4 * blockIdx.x + i) * (6 * DM), 4 * DM);
    }
    if (warp == 11) l2_prefetch_e((const char*)p.x + (size_t)blockIdx.x * 14336, 14336);
    if (lane == 0 && warp < 9 && warp != 6 && warp != 7) {
        const int i0 = warp == 8 ? 0 : 8 + 8 * warp, cnt = warp == 0 || warp == 8 ? 1 : warp < 3 ? 2 : 8;
#pragma unroll
        for (int k = 0; k < 8; k++) if (i0 + k != B_WMFULL) mbar_init(BAR(i0 + k), cnt);
        if (warp == 8) mbar_init(BAR(B_WMFULL), 1);
        asm volatile("fence.mbarrier_init.release.cluster;" ::: "memory");
        fence_async_smem();
    }

    if (warp >= 8) {
        const int lane = fresh_tid() & 31;
        const bool early = kh == 0, gemv = r < 14;
        const int mcol = early ? 16 * (4 * r + nq) : 2 * DM + 32 * (4 * r + nq);
        const uint32_t wmbuf = sb + OFF_Y + HALF;
        if (warp == 8) {
            __syncwarp();
            expect_e(BAR(B_WMFULL), gemv ? 28672 >> early : 0);
            if (early && gemv) { tma3_e(wmbuf, &p.wm, mcol, 0, 0, BAR(B_WMFULL)); tma3_e(wmbuf + 7168, &p.wm, mcol, 224, 0, BAR(B_WMFULL)); }
#pragma unroll
            for (int kb = 0; kb < 7; kb++) {
                expect_e(BAR(B_XFULL + kb), 16384);
                tma3_e(sb + OFF_X + kb * 16384, &p.xm, 64 * kb, 128 * r, 0, BAR(B_XFULL + kb));
            }
        }
        asm volatile("setmaxnreg.dec.sync.aligned.u32 56;");
        if (warp == 9) {
#pragma unroll
            for (int i = 56; i < 64; i++) init_e(BAR(i), 1);
            fence_async_smem();
        }
        bar_arrive(0, 384);
        asm volatile("barrier.cluster.arrive.relaxed.aligned;" ::: "memory");
        if (warp == 8) {
            mbar_wait(BAR(B_XFULL), 0);
            l2_prefetch_e((const char*)p.wqkv + (size_t)b * 9408, 9408);
#pragma unroll 1
            for (int mt = 0; mt < 4; mt++) {
                if (mt == 1) bar_sync(9, 384);
                if (mt == 3) mbar_wait(BAR(B_WMFREE), 0);
                if (mt == 1 && early) mbar_wait(BAR(B_WMFREE), 0);
                if (mt) mbar_wait(BAR(mt == 1 ? B_FULLK : mt == 2 ? B_MOD1 : B_VRFULL), 0);
                const uint32_t bar = BAR(mt == 3 ? B_WOFULL : B_FULLK + mt), dst = sb + (mt < 2 ? OFF_Y : OFF_X) + (mt & 1) * HALF;
                const int c0 = (mt < 2 ? DM + DM * mt : 0) + 56 * j - 8 * kh;
                expect_e(bar, HALF);
                tma3_e(dst, mt == 3 ? &p.wo : &p.qkv, c0, 0, 0, bar);
                tma3_e(dst + HALF / 2, mt == 3 ? &p.wo : &p.qkv, c0, 224, 0, bar);
            }
        } else {
            if (warp == 10 && lane < 13) asm volatile("prefetch.tensormap [%0];" ::"l"(&p.wm + lane) : "memory");
            bar_sync(9, 384);
            if (warp == 11 && early) {
                const uint32_t target = lds1(sb + M_EPOCH) + 1;
                mbar_wait(BAR(B_GEMV), 0);
                float sum = 0.f;
#pragma unroll
                for (int i = 0; i < 8; i++) sum += *(const float*)(smem + OFF_Y + HALF + 29696 + (i * 16 + (lane & 15)) * 4);
                uint32_t* mg = g_mod + mcol + (lane & 15) + (lane >> 4) * 4 * 6 * DM;
                const uint32_t word = mod_word(sum, mcol, target);
                if (gemv) { st_relaxed(mg, word); st_relaxed(mg + 6 * DM, word); st_relaxed(mg + 12 * DM, word); st_relaxed(mg + 18 * DM, word); }
            }
        }
    }
    if (warp < 8) {
        const int w = (warp >> 2) ^ 1, wi = warp & 3;
#define COORDS const int t = fresh_tid() & 127, lane = t & 31, q = lane & 3, lr = lane >> 2, ra = 64 * w + 16 * wi + lr; \
        const uint32_t lx = (lane >> 4) ^ (lane & 7), mrow = (64 * w + 16 * wi + ((lane >> 3) & 1) * 8 + (lane & 7)) * 128; \
        (void)q; (void)lr; (void)ra; (void)lx; (void)mrow;
#define WAIT(i, par) mbar_wait_c(BAR(i), par)
        constexpr uint64_t DB128 = dconst(4096, 1024, 1);
        bar_sync(0, 384);
        asm volatile("barrier.cluster.arrive.relaxed.aligned;" ::: "memory");
        asm volatile("setmaxnreg.inc.sync.aligned.u32 224;");
        PROFC(0);
        uint32_t xr[16];
        {
            COORDS
            uint32_t h[112];
            LnRow ca, cb;
            const int mi = min(128 * w + t, 223);
            const uint4* msrc = mod_src(mi, r, j, false);
            uint4 mv;
            {
                float ds[4] = {}, da[2][4] = {}, db[2][4] = {};
                const uint32_t ONE2 = 0x3F803F80u;
#pragma unroll
                for (int kb = 0; kb < 7; kb++) {
                    if (kb == GEMV_AT) {
                        const int wd = fresh_tid();
                        if (wd == 255) { sts1(sb + M_EPOCH, cw / NCTA); cw = 0; }
                        sts1(sb + OFF_Y + HALF + 28672 + (wd >> 3) * 32 + (wd & 3) * 8 + (wd & 4), pack2(silu_bf(cw & 0xFFFFu), silu_bf(cw >> 16)));
                        bar_arrive(9, 384);
                        bar_sync(3, 256);
                        if (kh == 0) { WAIT(B_WMFULL, 0); gemv_part(sb + OFF_Y + HALF, warp, lane); warp_arrive(BAR(B_GEMV)); }
                    }
                    WAIT(B_XFULL + kb, 0);
#pragma unroll
                    for (int k4 = 0; k4 < 4; k4++) ldsm4(sb + OFF_X + mrow + kb * 16384 + (((2 * k4) ^ lx) << 4), h + 16 * kb + 4 * k4);
#pragma unroll
                    for (int k4 = 0; k4 < 4; k4++) {
                        const uint32_t* f = h + 16 * kb + 4 * k4;
                        mma16816(ds, f[0], f[1], f[2], f[3], ONE2, ONE2);
                        mma1688(da[0], f[0], f[1], f[0]); mma1688(db[0], f[0], f[1], f[1]);
                        mma1688(da[1], f[2], f[3], f[2]); mma1688(db[1], f[2], f[3], f[3]);
                    }
                }
#pragma unroll
                for (int i = 0; i < 4; i++) {
                    const int ch = 7 * j + 2 * i + (lane >> 4);
                    ldsm4(sb + OFF_X + mrow + (ch >> 3) * 16384 + (((ch ^ lane) & 7) << 4), xr + 4 * i);
                }
                mv = ld_relaxed4(msrc);
                warp_arrive(BAR(B_XFREE));
                float qa = (lr & 1) ? da[0][1] + da[1][1] : da[0][0] + da[1][0];
                float qb = (lr & 1) ? db[0][3] + db[1][3] : db[0][2] + db[1][2];
                const int src = (lane & ~3) | (lr >> 1);
                qa = __shfl_sync(~0u, qa, src);
                qb = __shfl_sync(~0u, qb, src);
                ca = ln_coeffs(ds[0] * (1.f / DM), qa * (1.f / DM));
                cb = ln_coeffs(ds[2] * (1.f / DM), qb * (1.f / DM));
#pragma unroll
                for (int i = 0; i < 4 * NPRE; i += 2) { h[i] = ln_norm(h[i], ca); h[i + 1] = ln_norm(h[i + 1], cb); }
            }
            PROFC(1);
            {
                float ak[28], av[28], aq[28];
                uint32_t kp[14], vp[14];
                const uint64_t bq0 = (DB128 & ~0xFFFFFFFFull) | (mkdesc(sb + OFF_X, DB128) + kh), bk0 = bq0 + (OFF_Y >> 4), bv0 = bk0 + (HALF >> 4);
                uint32_t* kvg = act + RB_KV + j * 7168 + (8 * w + 2 * wi) * 224 + lane;
                mod_store(sb, mv, msrc, mi);
                bar_sync(3, 256);
                if (warp == 0) warp_arrive(BAR(B_MOD1));
                WAIT(B_FULLK, 0);
                PROFC(2);
                reg_def<28>(ak);
#pragma unroll
                for (int g4 = 0; g4 < 4; g4++) {
#pragma unroll
                    for (int ks = 7 * g4; ks < 7 * g4 + 7; ks++) {
                        const uint4 st = *(const uint4*)(smem + M_ST + ks * 64 + q * 16);
                        if (ks >= NPRE) {
                            h[4 * ks] = ln_norm(h[4 * ks], ca); h[4 * ks + 1] = ln_norm(h[4 * ks + 1], cb);
                            h[4 * ks + 2] = ln_norm(h[4 * ks + 2], ca); h[4 * ks + 3] = ln_norm(h[4 * ks + 3], cb);
                        }
                        h[4 * ks] = ln_mod(h[4 * ks], st.x, st.y); h[4 * ks + 1] = ln_mod(h[4 * ks + 1], st.x, st.y);
                        h[4 * ks + 2] = ln_mod(h[4 * ks + 2], st.z, st.w); h[4 * ks + 3] = ln_mod(h[4 * ks + 3], st.z, st.w);
                    }
                    WG_FENCE();
#pragma unroll
                    for (int ks = 7 * g4; ks < 7 * g4 + 7; ks++) wgmma_rl_56(ak, h[4 * ks], h[4 * ks + 1], h[4 * ks + 2], h[4 * ks + 3], bk0 + ks * 128, ks != 0);
                }
                WG_COMMIT();
                PROFC(3);
                reg_def<28>(av);
                WG_WAIT(0);
                reg_fence<28>(ak);
#pragma unroll
                for (int g = 0; g < 7; g++) {
                    kp[2 * g] = pack2(ak[4 * g], ak[4 * g + 1]); kp[2 * g + 1] = pack2(ak[4 * g + 2], ak[4 * g + 3]);
                    kvg[g * 32] = kp[2 * g]; kvg[224 + g * 32] = kp[2 * g + 1];
                }
                warp_arrive(BAR(B_PUB));
                PROFC(4);
                WAIT(B_FULLV, 0);
                WG_FENCE();
#pragma unroll
                for (int ks = 0; ks < 28; ks++) wgmma_rl_56(av, h[4 * ks], h[4 * ks + 1], h[4 * ks + 2], h[4 * ks + 3], bv0 + ks * 128, ks != 0);
                WG_COMMIT();
                reg_def<28>(aq);
                WAIT(B_FULLQ, 0);
                WG_FENCE();
#pragma unroll
                for (int ks = 0; ks < VPRE; ks++) wgmma_rl_56(aq, h[4 * ks], h[4 * ks + 1], h[4 * ks + 2], h[4 * ks + 3], bq0 + ks * 128, ks != 0);
                WG_COMMIT();
                WG_WAIT(1);
                reg_fence<28>(av);
#pragma unroll
                for (int g = 0; g < 7; g++) {
                    vp[2 * g] = pack2(av[4 * g], av[4 * g + 1]); vp[2 * g + 1] = pack2(av[4 * g + 2], av[4 * g + 3]);
                    kvg[3584 + g * 32] = vp[2 * g]; kvg[3584 + 224 + g * 32] = vp[2 * g + 1];
                }
                warp_arrive(BAR(B_PUB + 1));
                PROFC(5);
                WG_FENCE();
#pragma unroll
                for (int ks = VPRE; ks < 28; ks++) wgmma_rl_56(aq, h[4 * ks], h[4 * ks + 1], h[4 * ks + 2], h[4 * ks + 3], bq0 + ks * 128, ks != 0);
                WG_COMMIT();
                WAIT(B_PUB + 1, 0);
                const uint32_t rg = 8 * w + 2 * wi + ((lane >> 3) & 1);
                const uint32_t ko = sb + OFF_Y + Y_KOWN + rg * 896 + (lane & 7) * 16, qo = sb + OFF_Y + Y_Q + rg * 1024 + (lane >> 4) * 128 + (lane & 7) * 16;
#pragma unroll
                for (int g = 0; g < 6; g += 2) {
                    stsm4(ko + (g + (lane >> 4)) * 128, kp[2 * g], kp[2 * g + 1], kp[2 * g + 2], kp[2 * g + 3]);
                    stsm4(ko + (Y_VOWN - Y_KOWN) + (g + (lane >> 4)) * 128, vp[2 * g], vp[2 * g + 1], vp[2 * g + 2], vp[2 * g + 3]);
                }
                stsm4(ko + (lane >> 4) * (Y_VOWN - Y_KOWN) + 6 * 128, kp[12], kp[13], vp[12], vp[13]);
                WG_WAIT(0);
                reg_fence<28>(aq);
                __syncwarp();
                if (lane < 3 && w == 1) mbar_arrive(BAR(B_EMPTY + lane));
                uint32_t qp[14];
#pragma unroll
                for (int i = 0; i < 14; i++) qp[i] = pack2(aq[2 * i], aq[2 * i + 1]);
                stsm4(qo, qp[0], qp[1], qp[2], qp[3]);
                stsm4(qo + 256, qp[4], qp[5], q < 2 ? qp[6] : 0u, q < 2 ? qp[7] : 0u);
                stsm4(qo + 512, q < 2 ? 0u : qp[6], q < 2 ? 0u : qp[7], qp[8], qp[9]);
                stsm4(qo + 768, qp[10], qp[11], qp[12], qp[13]);
                fence_async_smem();
                if (w == 0) { bar_arrive(4, 256); bar_sync(1, 128); } else { bar_arrive(5, 256); bar_sync(4, 256); }
            }
        }
        PROFC(6);
        WAIT(B_KRFULL, 0);
        PROFC(7);
        {
#pragma unroll 1
            for (int hf = 0; hf < 2; hf++) {
                COORDS
                if (hf > w) bar_sync(5, 256);
                float s[160];
                const float CS = 0.18898223650461361f * 1.4426950408889634f;
                const float NEG = __int_as_float(0xFF800000);
                constexpr uint64_t DQ = dconst(128, 1024, 0), DK = dconst(128, 896, 0);
                {
                    const uint32_t qd = mkdesc(sb + OFF_Y + Y_Q + hf * 8192 + w * 512, DQ), kd = mkdesc(sb + OFF_Y + Y_K + hf * 8 * 896 + w * 384, DK);
                    reg_def<160>(s);
                    WG_FENCE();
                    wgmma_sk_160<DQ, DK>(s, qd, kd, 0);
                    wgmma_sk_160<DQ, DK>(s, qd + 16, kd + 16, 1);
                    wgmma_sk_160<DQ, DK>(s + 80, qd, kd + 20 * 56, 0);
                    wgmma_sk_160<DQ, DK>(s + 80, qd + 16, kd + 20 * 56 + 16, 1);
                    WG_COMMIT();
                    WG_WAIT(0);
                    reg_fence<160>(s);
                }
                if (r < 2) {
                    const int pmin = 4 - 2 * r - hf;
#pragma unroll
                    for (int p4 = 0; p4 < 4; p4++)
                        if (p4 < pmin) {
#pragma unroll
                            for (int i = 0; i < 32; i++) asm volatile("mov.b32 %0, 0xFF800000;" : "=f"(s[32 * p4 + i]));
                        }
                }
                const bool c0 = 2 * q > lr, c1 = 2 * q + 1 > lr;
#pragma unroll
                for (int pp = 0; pp < 4; pp++) {
                    const bool me = pp == wi;
                    float* e = s + 8 * pp;
                    if (me && !c0) { e[0] = NEG; e[6] = NEG; }
                    if (me && !c1) { e[1] = NEG; e[7] = NEG; }
                    if (me) { e[2] = NEG; e[3] = NEG; }
                    e = s + 8 * (pp + 16);
                    if (me && c0) { e[0] = NEG; e[6] = NEG; }
                    if (me && c1) { e[1] = NEG; e[7] = NEG; }
                    if (me) { e[4] = NEG; e[5] = NEG; }
                }
#pragma unroll
                for (int i = 0; i < 24; i++) s[i] = (i >> 3) < wi ? s[136 + i] : s[i];
                int i0 = 0x80000000, i1 = 0x80000000, i2 = 0x80000000, i3 = 0x80000000;
#pragma unroll
                for (int pp = 0; pp < 17; pp++) {
                    const float* e = s + 8 * pp;
                    i0 = __vimax3_s32(i0, __float_as_int(e[0]), __float_as_int(e[1])); i1 = __vimax3_s32(i1, __float_as_int(e[2]), __float_as_int(e[3]));
                    i2 = __vimax3_s32(i2, __float_as_int(e[4]), __float_as_int(e[5])); i3 = __vimax3_s32(i3, __float_as_int(e[6]), __float_as_int(e[7]));
                }
                i0 = max(i0, i2); i1 = max(i1, i3);
                i0 = max(i0, __shfl_xor_sync(~0u, i0, 1)); i1 = max(i1, __shfl_xor_sync(~0u, i1, 1));
                i0 = max(i0, __shfl_xor_sync(~0u, i0, 2)); i1 = max(i1, __shfl_xor_sync(~0u, i1, 2));
                if (__any_sync(~0u, (i0 | i1) < 0)) {
                    uint32_t u0 = ~0u, u1 = ~0u, u2 = ~0u, u3 = ~0u;
#pragma unroll
                    for (int pp = 0; pp < 17; pp++) {
                        const float* e = s + 8 * pp;
                        u0 = __vimin3_u32(u0, __float_as_uint(e[0]), __float_as_uint(e[1])); u1 = __vimin3_u32(u1, __float_as_uint(e[2]), __float_as_uint(e[3]));
                        u2 = __vimin3_u32(u2, __float_as_uint(e[4]), __float_as_uint(e[5])); u3 = __vimin3_u32(u3, __float_as_uint(e[6]), __float_as_uint(e[7]));
                    }
                    u0 = min(u0, u2); u1 = min(u1, u3);
                    u0 = min(u0, __shfl_xor_sync(~0u, u0, 1)); u1 = min(u1, __shfl_xor_sync(~0u, u1, 1));
                    u0 = min(u0, __shfl_xor_sync(~0u, u0, 2)); u1 = min(u1, __shfl_xor_sync(~0u, u1, 2));
                    if (i0 < 0) i0 = u0;
                    if (i1 < 0) i1 = u1;
                }
                const float ma = __int_as_float(i0), mb = __int_as_float(i1);
                const float na = -ma * CS, nb = -mb * CS;
                PROFC(8 + 3 * hf);
                {
                    WAIT(B_VRFULL, 0);
                    float o[16] = {}, rs[4] = {};
                    const uint32_t va = sb + OFF_Y + Y_VR + (8 * hf + ((lane >> 3) & 1)) * 896 + (3 * w + (lane >> 4)) * 128 + (lane & 7) * 16;
                    constexpr uint32_t OWN = Y_VOWN - 32 * 896;
#pragma unroll
                    for (int pp = 0; pp < 17; pp++) {
                        uint32_t B[8];
                        const uint32_t v = va + pp * 1792 + (pp < 3 ? (pp < wi ? 17 * 1792 + OWN : 0) : pp == 16 ? OWN : pp >= 12 ? hf * OWN : 0);
                        ldsm4t(v, B); ldsm4t(v + 256, B + 4);
                        float e[8];
#pragma unroll
                        for (int i = 0; i < 8; i++) e[i] = ex2(fmaf(s[8 * pp + i], CS, (i & 2) ? nb : na));
                        const uint32_t p0 = pack2(e[0], e[1]), p1 = pack2(e[2], e[3]), p2 = pack2(e[4], e[5]), p3 = pack2(e[6], e[7]);
                        mma16816(rs, p0, p1, p2, p3, 0x3F803F80u, 0x3F803F80u);
#pragma unroll
                        for (int g = 0; g < 4; g++) mma16816(o + 4 * g, p0, p1, p2, p3, B[2 * g], B[2 * g + 1]);
                    }
                    PROFC(9 + 3 * hf);
                    const float ia = rcp(rs[0]), ib = rcp(rs[2]);
                    uint32_t* og = act + RB_O + hf * 14336 + (7 * j + 3 * w) * 256 + wi * 64 + lane;
#pragma unroll
                    for (int g = 0; g < 4; g++) {
                        if ((g == 3 - 3 * w) ? ((q >> 1) == w) : true) {
                            og[g * 256] = pack2(o[4 * g] * ia, o[4 * g + 1] * ia);
                            og[g * 256 + 32] = pack2(o[4 * g + 2] * ib, o[4 * g + 3] * ib);
                        }
                    }
                    warp_arrive(BAR(B_PUB + 2 + hf));
                    PROFC(10 + 3 * hf);
                }
            }
        }
        uint32_t x1p[14];
        COORDS
        constexpr uint64_t DT = dconst(1024, 128, 0);
        const uint32_t epoch = lds1(sb + M_EPOCH);
        const int tile = opaque((epoch & 1) * 2 + w);
        {
            float ac[28];
            const uint32_t ad = mkdesc(sb + (w ? OFF_Y + HALF : OFF_X), DT), bd = mkdesc(sb + OFF_X + HALF, DB128) + kh;
            WAIT(B_WOFULL, 0);
            WAIT(B_MOD1, 1);
            WAIT(B_GFULL + w, 0);
            PROFC(28);
            reg_def<28>(ac);
#pragma unroll 1
            for (int u = 0; u < 4; u++) {
                if (u == 2) WAIT(B_XFULL + 2 + w, 1);
                WG_FENCE();
#pragma unroll
                for (int i = 0; i < 7; i++) wgmma_ss_56<DT, DB128>(ac, ad + (7 * u + i) * 128, bd + (7 * u + i) * 128, (u | i) != 0);
            }
            WG_COMMIT();
            WG_WAIT(0);
            reg_fence<28>(ac);
            PROFC(14);
            __syncwarp();
            if (lane < 3) mbar_arrive(BAR(B_EMPTY + 4 - w + lane));
            if (lane < 3 && w == 0) mbar_arrive(BAR(B_EMPTY + lane));
            float ds[4] = {}, da[4] = {}, db[4] = {};
            uint32_t* xo = act + RB_X1 + tile * 14336 + 7 * j * 256 + wi * 64 + lane;
#pragma unroll
            for (int g = 0; g < 7; g++) {
                const float2 ga = *(const float2*)(smem + M_G + (8 * g + 2 * q) * 4);
                x1p[2 * g] = pack2(fmaf(ga.x, ac[4 * g], bf_lo(xr[2 * g])), fmaf(ga.y, ac[4 * g + 1], bf_hi(xr[2 * g])));
                x1p[2 * g + 1] = pack2(fmaf(ga.x, ac[4 * g + 2], bf_lo(xr[2 * g + 1])), fmaf(ga.y, ac[4 * g + 3], bf_hi(xr[2 * g + 1])));
                st_relaxed(xo + g * 256, nz(x1p[2 * g])); st_relaxed(xo + g * 256 + 32, nz(x1p[2 * g + 1]));
                mma1688(ds, x1p[2 * g], x1p[2 * g + 1], 0x3F803F80u);
                mma1688(da, x1p[2 * g], x1p[2 * g + 1], x1p[2 * g]);
                mma1688(db, x1p[2 * g], x1p[2 * g + 1], x1p[2 * g + 1]);
            }
            const int src = (lane & ~3) | (lr >> 1);
            const float qa = __shfl_sync(~0u, (lr & 1) ? da[1] : da[0], src), qb = __shfl_sync(~0u, (lr & 1) ? db[3] : db[2], src);
            const float kk = (q & 1) ? ((q & 2) ? qb : qa) : ((q & 2) ? ds[2] : ds[0]);
            st_relaxed(act + RB_ST + ((tile * 8 + j) * 64 + 16 * wi + lr + 4 * (q & 2)) * 2 + (q & 1), nz(__float_as_uint(kk)));
            if (lane < 8) st_relaxed(g_flag + (8 * r + lane) * 192 + 128 + 32 * w + 4 * j + wi, epoch + 1);
        }
        PROFC(15);
        uint32_t h2a[32], h2b[24];
        {
            const int fa = pass_f(fs, 0), fb = pass_f(fs, 1), fc = pass_f(fs, 2);
            uint32_t* h2g = act + RB_H2 + (8 * w + 2 * wi) * 32 + lane;
            const uint32_t a0 = mkdesc(sb + OFF_Y + w * HALF, DT);
            {
                LnRow ca, cb;
                {
                    const uint32_t* sg = act + RB_ST + ((tile * 8 + 2 * q) * 64 + 16 * wi + lr) * 2;
                    uint2 u[4];
                    WAIT(B_FULLV + w, 1);
                    PROFC(16);
#pragma unroll
                    for (int i = 0; i < 4; i++) { const float2 v = lds2f(sb + OFF_X + X_STAT + w * 49152 + ((2 * q + (i >> 1)) * 64 + 16 * wi + lr + 8 * (i & 1)) * 8); u[i] = make_uint2(__float_as_uint(v.x), __float_as_uint(v.y)); }
                    while (__any_sync(~0u, min(min(min(u[0].x, u[0].y), min(u[1].x, u[1].y)), min(min(u[2].x, u[2].y), min(u[3].x, u[3].y))) == 0u)) {
#pragma unroll
                        for (int i = 0; i < 4; i++) u[i] = ld_relaxed2(sg + (i >> 1) * 128 + (i & 1) * 16);
                    }
                    warp_arrive(BAR(B_EMPTY + 3 + 3 * w));
                    float v[4] = {__uint_as_float(u[0].x) + __uint_as_float(u[2].x), __uint_as_float(u[0].y) + __uint_as_float(u[2].y),
                                  __uint_as_float(u[1].x) + __uint_as_float(u[3].x), __uint_as_float(u[1].y) + __uint_as_float(u[3].y)};
#pragma unroll
                    for (int i = 0; i < 4; i++) { v[i] += __shfl_xor_sync(~0u, v[i], 1); v[i] += __shfl_xor_sync(~0u, v[i], 2); }
                    ca = ln_coeffs(v[0] * (1.f / DM), v[1] * (1.f / DM));
                    cb = ln_coeffs(v[2] * (1.f / DM), v[3] * (1.f / DM));
                }
                const uint32_t ha = sb + OFF_Y + w * HALF + (lane >> 4) * 1024 + (2 * wi + ((lane >> 3) & 1)) * 128 + (lane & 7) * 16;
                const uint32_t sta = sb + M_ST + q * 16;
                const uint32_t* xg = act + RB_X1 + tile * 14336 + (lane >> 4) * 256 + wi * 64 + (lane & 15) * 4;
                uint32_t x[8];
                const uint32_t xs = sb + OFF_Y + w * HALF + (lane >> 4) * 1024 + wi * 256 + (lane & 15) * 16;
                uint4 st[2];
                auto load = [&](int s) {
                    if (s == 4) mbar_wait_c(BAR(B_XFULL + 4 + w), 1);
                    ldsm4(ha + s * 4096, x); ldsm4(ha + s * 4096 + 2048, x + 4);
                    st[0] = lds4(sta + s * 128); st[1] = lds4(sta + s * 128 + 64);
                };
                auto prep = [&](int s, uint32_t* f) {
                    if (__any_sync(~0u, min(min(min(x[0], x[1]), min(x[2], x[3])), min(min(x[4], x[5]), min(x[6], x[7]))) == 0u)) {
                        WG_WAIT(0);
                        x1_fix(xg, xs, s);
                        ldsm4(ha + s * 4096, x); ldsm4(ha + s * 4096 + 2048, x + 4);
                    }
#pragma unroll
                    for (int i = 0; i < 2; i++) {
                        f[4 * i] = ln_mod(ln_norm(x[4 * i], ca), st[i].x, st[i].y); f[4 * i + 1] = ln_mod(ln_norm(x[4 * i + 1], cb), st[i].x, st[i].y);
                        f[4 * i + 2] = ln_mod(ln_norm(x[4 * i + 2], ca), st[i].z, st[i].w); f[4 * i + 3] = ln_mod(ln_norm(x[4 * i + 3], cb), st[i].z, st[i].w);
                    }
                    if (s < 13) load(s + 1);
                    stsm4(ha + s * 4096, f[0], f[1], f[2], f[3]); stsm4(ha + s * 4096 + 2048, f[4], f[5], f[6], f[7]);
                };
                float ac[128];
                uint32_t fr[3][8];
                uint64_t bd = (DB128 & ~0xFFFFFFFFull) | mkdesc(sb, DB128);
                reg_def<128>(ac);
                WAIT(B_GFULL + 2 + w, 0);
                load(0);
                prep(0, fr[0]);
                PROFC(17);
#pragma unroll
                for (int s = 0; s < 14; s++) {
                    const uint32_t* f = fr[s % 3];
                    WAIT(B_FULL + g1_slot(s), s >= 7);
                    WG_FENCE();
                    wgmma_rl_256(ac, f[0], f[1], f[2], f[3], bd, s != 0);
                    wgmma_rl_256(ac, f[4], f[5], f[6], f[7], bd + 128, 1);
                    bd += s == 6 ? p.zero - 6 * 1024ull : 1024;
                    WG_COMMIT();
                    if (s < 13) prep(s + 1, fr[(s + 1) % 3]);
                    if (s > 0) { WG_WAIT(1); warp_arrive(BAR(B_EMPTY + g1_slot(s - 1))); }
                }
                fence_async_smem();
                PROFC(18);
                WG_WAIT(0);
                reg_fence<128>(ac);
                warp_arrive(BAR(B_EMPTY + 6));
#pragma unroll
                for (int g = 0; g < 16; g++) {
                    h2a[2 * g] = hmul2(pack2_relu(ac[4 * g], ac[4 * g + 1]), pack2(ac[64 + 4 * g], ac[64 + 4 * g + 1]));
                    h2a[2 * g + 1] = hmul2(pack2_relu(ac[4 * g + 2], ac[4 * g + 3]), pack2(ac[64 + 4 * g + 2], ac[64 + 4 * g + 3]));
                }
                bar_sync(1 + w, 128);
            }
            PROFC(19);
            {
                float ac[64];
                reg_def<64>(ac);
                const uint32_t bx = mkdesc(sb, dconst(8192, 1024, 1));
#pragma unroll 1
                for (int s = 0; s < 7; s++) {
                    WAIT(B_FULL + s, 0);
                    const uint32_t ad = a0 + s * 512, bd = bx + (slot_off(s) >> 4);
                    WG_FENCE();
#pragma unroll
                    for (int k = 0; k < 4; k++) wgmma_ss_128<DT, DB128>(ac, ad + k * 128, bd + k * 128, (s | k) != 0);
                    WG_COMMIT();
                    if (s == 1) {
#pragma unroll
                        for (int g = 0; g < 16; g++) { h2g[(fa / 8 + g) * 512] = h2a[2 * g]; h2g[(fa / 8 + g) * 512 + 32] = h2a[2 * g + 1]; }
                        warp_arrive(BAR(B_PUB + 6));
                    }
                    if (s > 0) { WG_WAIT(1); warp_arrive(BAR(B_EMPTY + s - 1)); }
                }
                WG_WAIT(0);
                reg_fence<64>(ac);
                warp_arrive(BAR(B_EMPTY + 6));
#pragma unroll
                for (int g = 0; g < 8; g++) {
                    h2b[2 * g] = hmul2(pack2_relu(ac[4 * g], ac[4 * g + 1]), pack2(ac[32 + 4 * g], ac[32 + 4 * g + 1]));
                    h2b[2 * g + 1] = hmul2(pack2_relu(ac[4 * g + 2], ac[4 * g + 3]), pack2(ac[32 + 4 * g + 2], ac[32 + 4 * g + 3]));
                }
            }
            PROFC(27);
            {
                float ac[32];
                reg_def<32>(ac);
                const uint32_t bx = mkdesc(sb, dconst(4096, 512, 2));
#pragma unroll 1
                for (int s = 0; s < 7; s++) {
                    WAIT(B_FULL + (s >> 1), 1);
                    const uint32_t ad = a0 + s * 512, bd = bx + s * 512;
                    WG_FENCE();
#pragma unroll
                    for (int k = 0; k < 4; k++) wgmma_ss_64<DT, dconst(4096, 512, 2)>(ac, ad + k * 128, bd + k * 64, (s | k) != 0);
                    WG_COMMIT();
                    if (s == 1) {
#pragma unroll
                        for (int g = 0; g < 8; g++) { h2g[(fb / 8 + g) * 512] = h2b[2 * g]; h2g[(fb / 8 + g) * 512 + 32] = h2b[2 * g + 1]; }
                        warp_arrive(BAR(B_PUB + 7));
                    }
                    if (s > 0 && !(s & 1)) {
                        WG_WAIT(1);
                        __syncwarp();
                        if (lane < 3) mbar_arrive(BAR(B_EMPTY + (s >> 1) - 1 + (lane ? 4 + 3 * lane : 0)));
                    }
                }
                WG_WAIT(0);
                reg_fence<32>(ac);
                PROFC(20);
#pragma unroll
                for (int g = 0; g < 4; g++) {
                    h2b[16 + 2 * g] = hmul2(pack2_relu(ac[4 * g], ac[4 * g + 1]), pack2(ac[16 + 4 * g], ac[16 + 4 * g + 1]));
                    h2b[16 + 2 * g + 1] = hmul2(pack2_relu(ac[4 * g + 2], ac[4 * g + 3]), pack2(ac[16 + 4 * g + 2], ac[16 + 4 * g + 3]));
                    h2g[(fc / 8 + g) * 512] = h2b[16 + 2 * g]; h2g[(fc / 8 + g) * 512 + 32] = h2b[16 + 2 * g + 1];
                }
                warp_arrive(BAR(B_PUB + 8));
                asm volatile("barrier.cluster.wait.aligned;" ::: "memory");
                if (lane == 0) {
                    uint32_t rb;
                    asm volatile("mapa.shared::cluster.u32 %0, %1, %2;" : "=r"(rb) : "r"(BAR(B_PEER)), "r"(kh ^ 1));
                    asm volatile("mbarrier.arrive.relaxed.cluster.shared::cluster.b64 _, [%0];" ::"r"(rb) : "memory");
                }
            }
        }
        PROFC(21);
        {
            float ac[56];
            reg_def<56>(ac);
            constexpr uint64_t DAN = dconst(2048, 128, 0);
            constexpr uint64_t DW = dconst(128, 512, 0);
            const uint32_t bx = mkdesc(sb, DW);
#pragma unroll
            for (int e = 3; e < 7; e++) {
                if (e > 3) WAIT(B_FULL + e, 1);
                const uint64_t bd = ((DW & ~0xFFFFFFFFull) | bx) + (slot_off(e) >> 4);
                const uint32_t* hh = e == 3 ? h2b + 8 : e < 6 ? h2a + 16 * (e - 4) : h2b;
                WG_FENCE();
#pragma unroll
                for (int k = e == 3 ? 2 : 0; k < 4; k++) wgmma_rl_112(ac, hh[4 * k], hh[4 * k + 1], hh[4 * k + 2], hh[4 * k + 3], bd + (k >> 1) * 512 + (k & 1) * 16, e > 3 || k > 2);
                WG_COMMIT();
                if (e > 3) { WG_WAIT(1); warp_arrive(BAR(B_EMPTY + e - 1)); }
            }
            PROFC(22);
            const uint32_t ax = mkdesc(sb + 8192 + w * 1024, DAN);
            uint32_t eb_ = BAR(B_EMPTY + 6);
            uint64_t ord = RING_ORDER;
#pragma unroll 1
            for (int e = 0; e < 21; e++) {
                const uint32_t sl = ord & 15, so = slot_off(sl) >> 4;
                ord = e == 12 ? RING_ORDER : ord >> 4;
                mbar_wait_c(BAR(B_FULL + sl), e >= 13);
                WG_FENCE();
                wgmma_ss_112<DAN, DW>(ac, ax + so, bx + so, 1);
                wgmma_ss_112<DAN, DW>(ac, ax + so + 256, bx + so + 16, 1);
                WG_COMMIT();
                WG_WAIT(1);
                warp_arrive(eb_);
                eb_ = BAR(B_EMPTY + sl);
            }
            mbar_wait_cluster(BAR(B_PEER), 0);
            WG_WAIT(0);
            reg_fence<56>(ac);
            PROFC(24);
            uint32_t rdst, rbar;
            asm volatile("mapa.shared::cluster.u32 %0, %1, %2;" : "=r"(rdst) : "r"(sb + OFF_Y + Y_XCH + w * HALF + t * 16), "r"(kh ^ 1));
            asm volatile("mapa.shared::cluster.u32 %0, %1, %2;" : "=r"(rbar) : "r"(BAR(B_XCH + w)), "r"(kh ^ 1));
#pragma unroll
            for (int g = 0; g < 3; g++)
                asm volatile("st.async.shared::cluster.mbarrier::complete_tx::bytes.v4.b32 [%0], {%1,%2,%3,%4}, [%5];" ::"r"(rdst + g * 2048),
                             "r"(pack2(ac[28 + 8 * g], ac[29 + 8 * g])), "r"(pack2(ac[30 + 8 * g], ac[31 + 8 * g])), "r"(pack2(ac[32 + 8 * g], ac[33 + 8 * g])),
                             "r"(pack2(ac[34 + 8 * g], ac[35 + 8 * g])), "r"(rbar) : "memory");
            asm volatile("st.async.shared::cluster.mbarrier::complete_tx::bytes.v2.b32 [%0], {%1,%2}, [%3];" ::"r"(rdst + 6144 - t * 8),
                         "r"(pack2(ac[52], ac[53])), "r"(pack2(ac[54], ac[55])), "r"(rbar) : "memory");
            mbar_wait_cluster(BAR(B_XCH + w), 0);
            PROFC(25);
            uint32_t op[14], rv[14];
#pragma unroll
            for (int g = 0; g < 3; g++) *(uint4*)(rv + 4 * g) = *(const uint4*)(smem + OFF_Y + Y_XCH + w * HALF + t * 16 + g * 2048);
            *(uint2*)(rv + 12) = *(const uint2*)(smem + OFF_Y + Y_XCH + w * HALF + 6144 + t * 8);
#pragma unroll
            for (int i = 0; i < 14; i++) {
                const float2 gb = *(const float2*)(smem + M_G + 224 + (8 * (i >> 1) + 2 * q) * 4);
                op[i] = pack2(fmaf(gb.x, ac[2 * i] + bf_lo(rv[i]), bf_lo(x1p[i])), fmaf(gb.y, ac[2 * i + 1] + bf_hi(rv[i]), bf_hi(x1p[i])));
            }
            WAIT(B_EMPTY + 4, 1);
            const uint32_t oc = sb + OUT_STAGE + warp * 1792;
            const uint32_t oa = oc + (((lane >> 3) & 1) * 8 + (lane & 7)) * 112 + (lane >> 4) * 16;
            stsm4(oa, op[0], op[1], op[2], op[3]); stsm4(oa + 32, op[4], op[5], op[6], op[7]); stsm4(oa + 64, op[8], op[9], op[10], op[11]);
            asm volatile("stmatrix.sync.aligned.m8n8.x2.shared.b16 [%0], {%1,%2};" ::"r"(oa + 96), "r"(op[12]), "r"(op[13]));
            fence_async_smem();
            __syncwarp();
            asm volatile("{\n.reg .pred p;\nelect.sync _|p, 0xffffffff;\n@p cp.async.bulk.tensor.3d.global.shared::cta.bulk_group [%0, {%2, %3, %4}], [%1];\n"
                         "cp.async.bulk.commit_group;\ncp.async.bulk.wait_group.read 0;\n}" ::"l"(&p.om), "r"(oc), "r"(56 * j), "r"(128 * r + 64 * w + 16 * wi), "r"(0) : "memory");
        }
        PROFC(26);
        bar_sync(1 + w, 128);
        if (wi == 0) warp_arrive(BAR(B_DONE));
        return;
    }
    helper_late(p, r, j, warp PROF_ARGS);
}

#undef act
typedef CUresult (*EncodeFn)(CUtensorMap*, CUtensorMapDataType, cuuint32_t, void*, const cuuint64_t*, const cuuint64_t*, const cuuint32_t*,
                             const cuuint32_t*, CUtensorMapInterleave, CUtensorMapSwizzle, CUtensorMapL2promotion, CUtensorMapFloatOOBfill);

static void make_map(EncodeFn fn, CUtensorMap* m, const void* ptr, uint64_t d0, uint64_t d1, uint64_t d2, uint64_t s1, uint64_t s2,
                     uint32_t b0, uint32_t b1, uint32_t b2, CUtensorMapSwizzle sw) {
    cuuint64_t dims[3] = {d0, d1, d2}, strides[2] = {s1, s2};
    cuuint32_t box[3] = {b0, b1, b2}, es[3] = {1, 1, 1};
    CUresult rc = fn(m, CU_TENSOR_MAP_DATA_TYPE_BFLOAT16, 3, (void*)ptr, dims, strides, box, es, CU_TENSOR_MAP_INTERLEAVE_NONE, sw,
                     CU_TENSOR_MAP_L2_PROMOTION_L2_128B, CU_TENSOR_MAP_FLOAT_OOB_FILL_NONE);
    (void)rc;
}

extern "C" void kernel_launch(void* const* d_in, const int* in_sizes, int n_in, void* d_out, int out_size) {
    (void)in_sizes; (void)n_in; (void)out_size;
    static EncodeFn fn = nullptr;
    static uint32_t* act_base = nullptr;
    if (!fn) {
        cudaDriverEntryPointQueryResult st;
        cudaGetDriverEntryPoint("cuTensorMapEncodeTiled", (void**)&fn, cudaEnableDefault, &st);
        void* a = nullptr;
        cudaGetSymbolAddress(&a, g_act);
        act_base = (uint32_t*)(((uintptr_t)a + 0xFFFFF) & ~(uintptr_t)0xFFFFF);
        cudaFuncSetAttribute(fused_block_kernel, cudaFuncAttributeMaxDynamicSharedMemorySize, SMEM_BYTES);
    }
    Params p;
    p.x = (const bf16*)d_in[0];
    const bf16* wqkv = (const bf16*)d_in[1];
    p.wqkv = wqkv;
    p.wop = (const bf16*)d_in[2];
    p.wg = (const bf16*)d_in[4];
    p.wu = (const bf16*)d_in[5];
    p.wd = (const bf16*)d_in[6];
    p.c = (const bf16*)d_in[7];
    p.wmod = (const bf16*)d_in[8];
    p.out = (bf16*)d_out;
    p.zero = 0;
    p.actb = act_base;
    make_map(fn, &p.wm, p.wmod, 2688, 448, 1, 5376, 5376 * 448, 16, 224, 1, CU_TENSOR_MAP_SWIZZLE_NONE);
    make_map(fn, &p.wm2, p.wmod, 2688, 448, 1, 5376, 5376 * 448, 32, 224, 1, CU_TENSOR_MAP_SWIZZLE_NONE);
    make_map(fn, &p.om, p.out, 448, 2048, 1, 896, 896 * 2048, 56, 16, 1, CU_TENSOR_MAP_SWIZZLE_NONE);
    make_map(fn, &p.xm, p.x, 448, 2048, 1, 896, 896 * 2048, 64, 128, 1, CU_TENSOR_MAP_SWIZZLE_128B);
    make_map(fn, &p.qkv, wqkv, 1344, 448, 1, 2688, 2688 * 448, 64, 224, 1, CU_TENSOR_MAP_SWIZZLE_128B);
    make_map(fn, &p.wo, p.wop, 448, 448, 1, 896, 896 * 448, 64, 224, 1, CU_TENSOR_MAP_SWIZZLE_128B);
    make_map(fn, &p.ga, p.wg, 64, 448, 28, 3584, 128, 64, 32, 2, CU_TENSOR_MAP_SWIZZLE_128B);
    make_map(fn, &p.ua, p.wu, 64, 448, 28, 3584, 128, 64, 32, 2, CU_TENSOR_MAP_SWIZZLE_128B);
    make_map(fn, &p.gb, p.wg, 64, 448, 28, 3584, 128, 64, 64, 1, CU_TENSOR_MAP_SWIZZLE_128B);
    make_map(fn, &p.ub, p.wu, 64, 448, 28, 3584, 128, 64, 64, 1, CU_TENSOR_MAP_SWIZZLE_128B);
    make_map(fn, &p.gc, p.wg, 32, 448, 56, 3584, 64, 32, 64, 1, CU_TENSOR_MAP_SWIZZLE_64B);
    make_map(fn, &p.uc, p.wu, 32, 448, 56, 3584, 64, 32, 64, 1, CU_TENSOR_MAP_SWIZZLE_64B);
    make_map(fn, &p.dn, p.wd, 8, 1792, 56, 896, 16, 8, 32, 7, CU_TENSOR_MAP_SWIZZLE_NONE);
    fused_block_kernel<<<NCTA, 384, SMEM_BYTES>>>(p);
}
```

```cpp
#include <cuda_runtime.h>
#include <cuda_bf16.h>
#include <cuda.h>
#include <stdint.h>

typedef __nv_bfloat16 bf16;

template<uint64_t CA, uint64_t CB> __device__ __forceinline__ void wgmma_sk_160(float* d, uint32_t da, uint32_t db, int sd) {
  asm volatile("{\n.reg .pred p;\n.reg .b64 a, b;\nsetp.ne.b32 p, %82, 0;\nmov.b64 a, {%80, %83};\nmov.b64 b, {%81, %84};\n"
    "wgmma.mma_async.sync.aligned.m64n160k16.f32.bf16.bf16 {%0,%1,%2,%3,%4,%5,%6,%7,%8,%9,%10,%11,%12,%13,%14,%15,%16,%17,%18,%19,%20,%21,%22,%23,%24,%25,%26,%27,%28,%29,%30,%31,%32,%33,%34,%35,%36,%37,%38,%39,%40,%41,%42,%43,%44,%45,%46,%47,%48,%49,%50,%51,%52,%53,%54,%55,%56,%57,%58,%59,%60,%61,%62,%63,%64,%65,%66,%67,%68,%69,%70,%71,%72,%73,%74,%75,%76,%77,%78,%79}, a, b, p, 1, 1, 0, 0;\n}\n"
    : "+f"(d[0]),"+f"(d[1]),"+f"(d[2]),"+f"(d[3]),"+f"(d[4]),"+f"(d[5]),"+f"(d[6]),"+f"(d[7]),"+f"(d[8]),"+f"(d[9]),"+f"(d[10]),"+f"(d[11]),"+f"(d[12]),"+f"(d[13]),"+f"(d[14]),"+f"(d[15]),"+f"(d[16]),"+f"(d[17]),"+f"(d[18]),"+f"(d[19]),"+f"(d[20]),"+f"(d[21]),"+f"(d[22]),"+f"(d[23]),"+f"(d[24]),"+f"(d[25]),"+f"(d[26]),"+f"(d[27]),"+f"(d[28]),"+f"(d[29]),"+f"(d[30]),"+f"(d[31]),"+f"(d[32]),"+f"(d[33]),"+f"(d[34]),"+f"(d[35]),"+f"(d[36]),"+f"(d[37]),"+f"(d[38]),"+f"(d[39]),"+f"(d[40]),"+f"(d[41]),"+f"(d[42]),"+f"(d[43]),"+f"(d[44]),"+f"(d[45]),"+f"(d[46]),"+f"(d[47]),"+f"(d[48]),"+f"(d[49]),"+f"(d[50]),"+f"(d[51]),"+f"(d[52]),"+f"(d[53]),"+f"(d[54]),"+f"(d[55]),"+f"(d[56]),"+f"(d[57]),"+f"(d[58]),"+f"(d[59]),"+f"(d[60]),"+f"(d[61]),"+f"(d[62]),"+f"(d[63]),"+f"(d[64]),"+f"(d[65]),"+f"(d[66]),"+f"(d[67]),"+f"(d[68]),"+f"(d[69]),"+f"(d[70]),"+f"(d[71]),"+f"(d[72]),"+f"(d[73]),"+f"(d[74]),"+f"(d[75]),"+f"(d[76]),"+f"(d[77]),"+f"(d[78]),"+f"(d[79])
    : "r"(da), "r"(db), "r"(sd), "n"((uint32_t)(CA >> 32)), "n"((uint32_t)(CB >> 32)));
}
__device__ __forceinline__ void wgmma_rl_56(float* d, uint32_t a0, uint32_t a1, uint32_t a2, uint32_t a3, uint64_t db, int sd) {
  asm volatile("{\n.reg .pred p;\nsetp.ne.b32 p, %33, 0;\n"
    "wgmma.mma_async.sync.aligned.m64n56k16.f32.bf16.bf16 {%0,%1,%2,%3,%4,%5,%6,%7,%8,%9,%10,%11,%12,%13,%14,%15,%16,%17,%18,%19,%20,%21,%22,%23,%24,%25,%26,%27}, {%28,%29,%30,%31}, %32, p, 1, 1, 1;\n}\n"
    : "+f"(d[0]),"+f"(d[1]),"+f"(d[2]),"+f"(d[3]),"+f"(d[4]),"+f"(d[5]),"+f"(d[6]),"+f"(d[7]),"+f"(d[8]),"+f"(d[9]),"+f"(d[10]),"+f"(d[11]),"+f"(d[12]),"+f"(d[13]),"+f"(d[14]),"+f"(d[15]),"+f"(d[16]),"+f"(d[17]),"+f"(d[18]),"+f"(d[19]),"+f"(d[20]),"+f"(d[21]),"+f"(d[22]),"+f"(d[23]),"+f"(d[24]),"+f"(d[25]),"+f"(d[26]),"+f"(d[27])
    : "r"(a0), "r"(a1), "r"(a2), "r"(a3), "l"(db), "r"(sd));
}
template<uint64_t CA, uint64_t CB> __device__ __forceinline__ void wgmma_ss_56(float* d, uint32_t da, uint32_t db, int sd) {
  asm volatile("{\n.reg .pred p;\n.reg .b64 a, b;\nsetp.ne.b32 p, %30, 0;\nmov.b64 a, {%28, %31};\nmov.b64 b, {%29, %32};\n"
    "wgmma.mma_async.sync.aligned.m64n56k16.f32.bf16.bf16 {%0,%1,%2,%3,%4,%5,%6,%7,%8,%9,%10,%11,%12,%13,%14,%15,%16,%17,%18,%19,%20,%21,%22,%23,%24,%25,%26,%27}, a, b, p, 1, 1, 0, 1;\n}\n"
    : "+f"(d[0]),"+f"(d[1]),"+f"(d[2]),"+f"(d[3]),"+f"(d[4]),"+f"(d[5]),"+f"(d[6]),"+f"(d[7]),"+f"(d[8]),"+f"(d[9]),"+f"(d[10]),"+f"(d[11]),"+f"(d[12]),"+f"(d[13]),"+f"(d[14]),"+f"(d[15]),"+f"(d[16]),"+f"(d[17]),"+f"(d[18]),"+f"(d[19]),"+f"(d[20]),"+f"(d[21]),"+f"(d[22]),"+f"(d[23]),"+f"(d[24]),"+f"(d[25]),"+f"(d[26]),"+f"(d[27])
    : "r"(da), "r"(db), "r"(sd), "n"((uint32_t)(CA >> 32)), "n"((uint32_t)(CB >> 32)));
}
__device__ __forceinline__ void wgmma_rl_256(float* d, uint32_t a0, uint32_t a1, uint32_t a2, uint32_t a3, uint64_t db, int sd) {
  asm volatile("{\n.reg .pred p;\nsetp.ne.b32 p, %133, 0;\n"
    "wgmma.mma_async.sync.aligned.m64n256k16.f32.bf16.bf16 {%0,%1,%2,%3,%4,%5,%6,%7,%8,%9,%10,%11,%12,%13,%14,%15,%16,%17,%18,%19,%20,%21,%22,%23,%24,%25,%26,%27,%28,%29,%30,%31,%32,%33,%34,%35,%36,%37,%38,%39,%40,%41,%42,%43,%44,%45,%46,%47,%48,%49,%50,%51,%52,%53,%54,%55,%56,%57,%58,%59,%60,%61,%62,%63,%64,%65,%66,%67,%68,%69,%70,%71,%72,%73,%74,%75,%76,%77,%78,%79,%80,%81,%82,%83,%84,%85,%86,%87,%88,%89,%90,%91,%92,%93,%94,%95,%96,%97,%98,%99,%100,%101,%102,%103,%104,%105,%106,%107,%108,%109,%110,%111,%112,%113,%114,%115,%116,%117,%118,%119,%120,%121,%122,%123,%124,%125,%126,%127}, {%128,%129,%130,%131}, %132, p, 1, 1, 1;\n}\n"
    : "+f"(d[0]),"+f"(d[1]),"+f"(d[2]),"+f"(d[3]),"+f"(d[4]),"+f"(d[5]),"+f"(d[6]),"+f"(d[7]),"+f"(d[8]),"+f"(d[9]),"+f"(d[10]),"+f"(d[11]),"+f"(d[12]),"+f"(d[13]),"+f"(d[14]),"+f"(d[15]),"+f"(d[16]),"+f"(d[17]),"+f"(d[18]),"+f"(d[19]),"+f"(d[20]),"+f"(d[21]),"+f"(d[22]),"+f"(d[23]),"+f"(d[24]),"+f"(d[25]),"+f"(d[26]),"+f"(d[27]),"+f"(d[28]),"+f"(d[29]),"+f"(d[30]),"+f"(d[31]),"+f"(d[32]),"+f"(d[33]),"+f"(d[34]),"+f"(d[35]),"+f"(d[36]),"+f"(d[37]),"+f"(d[38]),"+f"(d[39]),"+f"(d[40]),"+f"(d[41]),"+f"(d[42]),"+f"(d[43]),"+f"(d[44]),"+f"(d[45]),"+f"(d[46]),"+f"(d[47]),"+f"(d[48]),"+f"(d[49]),"+f"(d[50]),"+f"(d[51]),"+f"(d[52]),"+f"(d[53]),"+f"(d[54]),"+f"(d[55]),"+f"(d[56]),"+f"(d[57]),"+f"(d[58]),"+f"(d[59]),"+f"(d[60]),"+f"(d[61]),"+f"(d[62]),"+f"(d[63]),"+f"(d[64]),"+f"(d[65]),"+f"(d[66]),"+f"(d[67]),"+f"(d[68]),"+f"(d[69]),"+f"(d[70]),"+f"(d[71]),"+f"(d[72]),"+f"(d[73]),"+f"(d[74]),"+f"(d[75]),"+f"(d[76]),"+f"(d[77]),"+f"(d[78]),"+f"(d[79]),"+f"(d[80]),"+f"(d[81]),"+f"(d[82]),"+f"(d[83]),"+f"(d[84]),"+f"(d[85]),"+f"(d[86]),"+f"(d[87]),"+f"(d[88]),"+f"(d[89]),"+f"(d[90]),"+f"(d[91]),"+f"(d[92]),"+f"(d[93]),"+f"(d[94]),"+f"(d[95]),"+f"(d[96]),"+f"(d[97]),"+f"(d[98]),"+f"(d[99]),"+f"(d[100]),"+f"(d[101]),"+f"(d[102]),"+f"(d[103]),"+f"(d[104]),"+f"(d[105]),"+f"(d[106]),"+f"(d[107]),"+f"(d[108]),"+f"(d[109]),"+f"(d[110]),"+f"(d[111]),"+f"(d[112]),"+f"(d[113]),"+f"(d[114]),"+f"(d[115]),"+f"(d[116]),"+f"(d[117]),"+f"(d[118]),"+f"(d[119]),"+f"(d[120]),"+f"(d[121]),"+f"(d[122]),"+f"(d[123]),"+f"(d[124]),"+f"(d[125]),"+f"(d[126]),"+f"(d[127])
    : "r"(a0), "r"(a1), "r"(a2), "r"(a3), "l"(db), "r"(sd));
}
template<uint64_t CA, uint64_t CB> __device__ __forceinline__ void wgmma_ss_128(float* d, uint32_t da, uint32_t db, int sd) {
  asm volatile("{\n.reg .pred p;\n.reg .b64 a, b;\nsetp.ne.b32 p, %66, 0;\nmov.b64 a, {%64, %67};\nmov.b64 b, {%65, %68};\n"
    "wgmma.mma_async.sync.aligned.m64n128k16.f32.bf16.bf16 {%0,%1,%2,%3,%4,%5,%6,%7,%8,%9,%10,%11,%12,%13,%14,%15,%16,%17,%18,%19,%20,%21,%22,%23,%24,%25,%26,%27,%28,%29,%30,%31,%32,%33,%34,%35,%36,%37,%38,%39,%40,%41,%42,%43,%44,%45,%46,%47,%48,%49,%50,%51,%52,%53,%54,%55,%56,%57,%58,%59,%60,%61,%62,%63}, a, b, p, 1, 1, 0, 1;\n}\n"
    : "+f"(d[0]),"+f"(d[1]),"+f"(d[2]),"+f"(d[3]),"+f"(d[4]),"+f"(d[5]),"+f"(d[6]),"+f"(d[7]),"+f"(d[8]),"+f"(d[9]),"+f"(d[10]),"+f"(d[11]),"+f"(d[12]),"+f"(d[13]),"+f"(d[14]),"+f"(d[15]),"+f"(d[16]),"+f"(d[17]),"+f"(d[18]),"+f"(d[19]),"+f"(d[20]),"+f"(d[21]),"+f"(d[22]),"+f"(d[23]),"+f"(d[24]),"+f"(d[25]),"+f"(d[26]),"+f"(d[27]),"+f"(d[28]),"+f"(d[29]),"+f"(d[30]),"+f"(d[31]),"+f"(d[32]),"+f"(d[33]),"+f"(d[34]),"+f"(d[35]),"+f"(d[36]),"+f"(d[37]),"+f"(d[38]),"+f"(d[39]),"+f"(d[40]),"+f"(d[41]),"+f"(d[42]),"+f"(d[43]),"+f"(d[44]),"+f"(d[45]),"+f"(d[46]),"+f"(d[47]),"+f"(d[48]),"+f"(d[49]),"+f"(d[50]),"+f"(d[51]),"+f"(d[52]),"+f"(d[53]),"+f"(d[54]),"+f"(d[55]),"+f"(d[56]),"+f"(d[57]),"+f"(d[58]),"+f"(d[59]),"+f"(d[60]),"+f"(d[61]),"+f"(d[62]),"+f"(d[63])
    : "r"(da), "r"(db), "r"(sd), "n"((uint32_t)(CA >> 32)), "n"((uint32_t)(CB >> 32)));
}
template<uint64_t CA, uint64_t CB> __device__ __forceinline__ void wgmma_ss_64(float* d, uint32_t da, uint32_t db, int sd) {
  asm volatile("{\n.reg .pred p;\n.reg .b64 a, b;\nsetp.ne.b32 p, %34, 0;\nmov.b64 a, {%32, %35};\nmov.b64 b, {%33, %36};\n"
    "wgmma.mma_async.sync.aligned.m64n64k16.f32.bf16.bf16 {%0,%1,%2,%3,%4,%5,%6,%7,%8,%9,%10,%11,%12,%13,%14,%15,%16,%17,%18,%19,%20,%21,%22,%23,%24,%25,%26,%27,%28,%29,%30,%31}, a, b, p, 1, 1, 0, 1;\n}\n"
    : "+f"(d[0]),"+f"(d[1]),"+f"(d[2]),"+f"(d[3]),"+f"(d[4]),"+f"(d[5]),"+f"(d[6]),"+f"(d[7]),"+f"(d[8]),"+f"(d[9]),"+f"(d[10]),"+f"(d[11]),"+f"(d[12]),"+f"(d[13]),"+f"(d[14]),"+f"(d[15]),"+f"(d[16]),"+f"(d[17]),"+f"(d[18]),"+f"(d[19]),"+f"(d[20]),"+f"(d[21]),"+f"(d[22]),"+f"(d[23]),"+f"(d[24]),"+f"(d[25]),"+f"(d[26]),"+f"(d[27]),"+f"(d[28]),"+f"(d[29]),"+f"(d[30]),"+f"(d[31])
    : "r"(da), "r"(db), "r"(sd), "n"((uint32_t)(CA >> 32)), "n"((uint32_t)(CB >> 32)));
}
template<uint64_t CA, uint64_t CB> __device__ __forceinline__ void wgmma_ss_112(float* d, uint32_t da, uint32_t db, int sd) {
  asm volatile("{\n.reg .pred p;\n.reg .b64 a, b;\nsetp.ne.b32 p, %58, 0;\nmov.b64 a, {%56, %59};\nmov.b64 b, {%57, %60};\n"
    "wgmma.mma_async.sync.aligned.m64n112k16.f32.bf16.bf16 {%0,%1,%2,%3,%4,%5,%6,%7,%8,%9,%10,%11,%12,%13,%14,%15,%16,%17,%18,%19,%20,%21,%22,%23,%24,%25,%26,%27,%28,%29,%30,%31,%32,%33,%34,%35,%36,%37,%38,%39,%40,%41,%42,%43,%44,%45,%46,%47,%48,%49,%50,%51,%52,%53,%54,%55}, a, b, p, 1, 1, 0, 1;\n}\n"
    : "+f"(d[0]),"+f"(d[1]),"+f"(d[2]),"+f"(d[3]),"+f"(d[4]),"+f"(d[5]),"+f"(d[6]),"+f"(d[7]),"+f"(d[8]),"+f"(d[9]),"+f"(d[10]),"+f"(d[11]),"+f"(d[12]),"+f"(d[13]),"+f"(d[14]),"+f"(d[15]),"+f"(d[16]),"+f"(d[17]),"+f"(d[18]),"+f"(d[19]),"+f"(d[20]),"+f"(d[21]),"+f"(d[22]),"+f"(d[23]),"+f"(d[24]),"+f"(d[25]),"+f"(d[26]),"+f"(d[27]),"+f"(d[28]),"+f"(d[29]),"+f"(d[30]),"+f"(d[31]),"+f"(d[32]),"+f"(d[33]),"+f"(d[34]),"+f"(d[35]),"+f"(d[36]),"+f"(d[37]),"+f"(d[38]),"+f"(d[39]),"+f"(d[40]),"+f"(d[41]),"+f"(d[42]),"+f"(d[43]),"+f"(d[44]),"+f"(d[45]),"+f"(d[46]),"+f"(d[47]),"+f"(d[48]),"+f"(d[49]),"+f"(d[50]),"+f"(d[51]),"+f"(d[52]),"+f"(d[53]),"+f"(d[54]),"+f"(d[55])
    : "r"(da), "r"(db), "r"(sd), "n"((uint32_t)(CA >> 32)), "n"((uint32_t)(CB >> 32)));
}
__device__ __forceinline__ void wgmma_rl_112(float* d, uint32_t a0, uint32_t a1, uint32_t a2, uint32_t a3, uint64_t db, int sd) {
  asm volatile("{\n.reg .pred p;\nsetp.ne.b32 p, %61, 0;\n"
    "wgmma.mma_async.sync.aligned.m64n112k16.f32.bf16.bf16 {%0,%1,%2,%3,%4,%5,%6,%7,%8,%9,%10,%11,%12,%13,%14,%15,%16,%17,%18,%19,%20,%21,%22,%23,%24,%25,%26,%27,%28,%29,%30,%31,%32,%33,%34,%35,%36,%37,%38,%39,%40,%41,%42,%43,%44,%45,%46,%47,%48,%49,%50,%51,%52,%53,%54,%55}, {%56,%57,%58,%59}, %60, p, 1, 1, 1;\n}\n"
    : "+f"(d[0]),"+f"(d[1]),"+f"(d[2]),"+f"(d[3]),"+f"(d[4]),"+f"(d[5]),"+f"(d[6]),"+f"(d[7]),"+f"(d[8]),"+f"(d[9]),"+f"(d[10]),"+f"(d[11]),"+f"(d[12]),"+f"(d[13]),"+f"(d[14]),"+f"(d[15]),"+f"(d[16]),"+f"(d[17]),"+f"(d[18]),"+f"(d[19]),"+f"(d[20]),"+f"(d[21]),"+f"(d[22]),"+f"(d[23]),"+f"(d[24]),"+f"(d[25]),"+f"(d[26]),"+f"(d[27]),"+f"(d[28]),"+f"(d[29]),"+f"(d[30]),"+f"(d[31]),"+f"(d[32]),"+f"(d[33]),"+f"(d[34]),"+f"(d[35]),"+f"(d[36]),"+f"(d[37]),"+f"(d[38]),"+f"(d[39]),"+f"(d[40]),"+f"(d[41]),"+f"(d[42]),"+f"(d[43]),"+f"(d[44]),"+f"(d[45]),"+f"(d[46]),"+f"(d[47]),"+f"(d[48]),"+f"(d[49]),"+f"(d[50]),"+f"(d[51]),"+f"(d[52]),"+f"(d[53]),"+f"(d[54]),"+f"(d[55])
    : "r"(a0), "r"(a1), "r"(a2), "r"(a3), "l"(db), "r"(sd));
}

constexpr int DM = 448;
constexpr int NCTA = 128;
#define WIN 5
#define NPRE 14
#define VPRE 3
constexpr int SPIN_LIMIT = 1 << 22;

constexpr uint32_t OFF_X = 0, OFF_Y = 114688, OFF_MISC = 229376, SMEM_BYTES = 232448;
constexpr uint32_t Y_VR = 0, Y_K = 28672, Y_KOWN = 57344, Y_VOWN = 71680, Y_Q = 86016;
constexpr uint32_t HALF = 57344;
constexpr uint32_t X_STAT = 49152;
constexpr uint32_t OUT_STAGE = 4 * 16384;
constexpr uint32_t M_BAR = OFF_MISC;
constexpr uint32_t M_ST = OFF_MISC + 512;
constexpr uint32_t M_G = OFF_MISC + 2304;
constexpr uint32_t M_EPOCH = OFF_MISC + 3040;
enum { B_XFULL = 0, B_FULLK = 7, B_FULLV = 8, B_FULLQ, B_KRFULL, B_VRFULL, B_WOFULL, B_XCH, B_MOD1 = 15, B_FULL = 16, B_WMFULL = 30,
       B_EMPTY = 32, B_PEER = 45, B_EPOCH,
       B_PUB = 47,
       B_XFREE = B_PUB + 4, B_GEMV,
       B_WMFREE = 56, B_HRDY, B_GFULL = B_HRDY + 3, B_DONE = 31 };

__device__ uint32_t g_ticket;
__device__ __align__(128) uint32_t g_mod[8 * 6 * DM];
__device__ __align__(128) uint32_t g_flag[144 * 192];
constexpr int RB_WORDS = 262144, RB_KV = 0, RB_O = 57344, RB_X1 = 86016, RB_H2 = 143360, RB_ST = 258048;
__device__ __align__(128) uint32_t g_act[17 * RB_WORDS];
__device__ __align__(128) uint32_t g_wd[56 * 4 * 1792];
#define PROFH(id)
#define PROFH1(id)
#define PROFC(id)

struct alignas(64) Params {
    CUtensorMap wm, wm2, om, xm, qkv, wo, ga, ua, gb, ub, gc, uc, dn;
    const bf16 *x, *c, *wqkv, *wmod, *wg, *wu, *wd, *wop;
    bf16* out;
    uint32_t* actb;
    uint32_t zero;
};

__device__ __forceinline__ void mbar_init(uint32_t bar, int cnt) { asm volatile("mbarrier.init.shared::cta.b64 [%0], %1;" ::"r"(bar), "r"(cnt) : "memory"); }
__device__ __forceinline__ void mbar_arrive(uint32_t bar) { asm volatile("mbarrier.arrive.shared::cta.b64 _, [%0];" ::"r"(bar) : "memory"); }
__device__ __forceinline__ void mbar_wait(uint32_t bar, uint32_t parity) {
    uint32_t ok; int n = 0;
    do {
        asm volatile("{\n.reg .pred p;\nmbarrier.try_wait.parity.shared::cta.b64 p, [%1], %2;\nselp.u32 %0, 1, 0, p;\n}" : "=r"(ok) : "r"(bar), "r"(parity) : "memory");
        if (++n > SPIN_LIMIT) __trap();
    } while (!ok);
}
__device__ __forceinline__ void mbar_wait_c(uint32_t bar, uint32_t parity) {
    asm volatile("{\n.reg .pred p;\nWL:\nmbarrier.try_wait.parity.shared::cta.b64 p, [%0], %1, 0x989680;\n@!p bra WL;\n}" ::"r"(bar), "r"(parity) : "memory");
}
__device__ __forceinline__ void mbar_wait_cluster(uint32_t bar, uint32_t parity) {
    asm volatile("{\n.reg .pred p;\nWL:\nmbarrier.try_wait.parity.acquire.cluster.shared::cta.b64 p, [%0], %1, 0x989680;\n@!p bra WL;\n}" ::"r"(bar), "r"(parity) : "memory");
}
__device__ __forceinline__ void warp_arrive(uint32_t bar) {
    __syncwarp();
    asm volatile("{\n.reg .pred p;\nelect.sync _|p, 0xffffffff;\n@p mbarrier.arrive.shared::cta.b64 _, [%0];\n}" ::"r"(bar) : "memory");
}
__device__ __forceinline__ int opaque(int v) { return __shfl_sync(~0u, v, 0); }
__device__ __forceinline__ int fresh_tid() { int v; asm volatile("mov.u32 %0, %%tid.x;" : "=r"(v)); return v; }
__device__ __forceinline__ void bar_sync(int id, int n) { asm volatile("bar.sync %0, %1;" ::"r"(id), "r"(n) : "memory"); }
__device__ __forceinline__ void bar_arrive(int id, int n) { asm volatile("bar.arrive %0, %1;" ::"r"(id), "r"(n) : "memory"); }
__device__ __forceinline__ void fence_async_smem() { asm volatile("fence.proxy.async.shared::cta;" ::: "memory"); }
__device__ __forceinline__ void fence_async_global() { asm volatile("fence.proxy.async.global;" ::: "memory"); }
__device__ __forceinline__ void fence_gpu() { asm volatile("fence.release.gpu;" ::: "memory"); }
__device__ __forceinline__ void expect_e(uint32_t bar, uint32_t bytes) {
    asm volatile("{\n.reg .pred p;\nelect.sync _|p, 0xffffffff;\n@p mbarrier.arrive.expect_tx.shared::cta.b64 _, [%0], %1;\n}" ::"r"(bar), "r"(bytes) : "memory");
}
__device__ __forceinline__ void tma3_e(uint32_t dst, const CUtensorMap* m, int c0, int c1, int c2, uint32_t bar) {
    asm volatile("{\n.reg .pred p;\nelect.sync _|p, 0xffffffff;\n@p cp.async.bulk.tensor.3d.shared::cluster.global.mbarrier::complete_tx::bytes [%0], [%1, {%3, %4, %5}], [%2];\n}"
                 ::"r"(dst), "l"(m), "r"(bar), "r"(c0), "r"(c1), "r"(c2) : "memory");
}
__device__ __forceinline__ void bulk_e(uint32_t dst, const void* src, uint32_t bytes, uint32_t bar) {
    asm volatile("{\n.reg .pred p;\nelect.sync _|p, 0xffffffff;\n@p cp.async.bulk.shared::cluster.global.mbarrier::complete_tx::bytes [%0], [%1], %2, [%3];\n}"
                 ::"r"(dst), "l"(src), "r"(bytes), "r"(bar) : "memory");
}
__device__ __forceinline__ void init_e(uint32_t bar, int cnt) {
    asm volatile("{\n.reg .pred p;\nelect.sync _|p, 0xffffffff;\n@p mbarrier.init.shared::cta.b64 [%0], %1;\n}" ::"r"(bar), "r"(cnt) : "memory");
}
__device__ __forceinline__ void l2_prefetch_e(const void* src, uint32_t bytes) {
    asm volatile("{\n.reg .pred p;\nelect.sync _|p, 0xffffffff;\n@p cp.async.bulk.prefetch.L2.global [%0], %1;\n}" ::"l"(src), "r"(bytes) : "memory");
}
__device__ __forceinline__ uint32_t ld_relaxed(const uint32_t* p) { uint32_t v; asm volatile("ld.relaxed.gpu.global.u32 %0, [%1];" : "=r"(v) : "l"(p) : "memory"); return v; }
__device__ __forceinline__ void st_relaxed(uint32_t* p, uint32_t v) { asm volatile("st.relaxed.gpu.global.u32 [%0], %1;" ::"l"(p), "r"(v) : "memory"); }
__device__ __forceinline__ uint4 ld_relaxed4(const uint4* p) { uint4 v; asm volatile("ld.relaxed.gpu.global.v4.u32 {%0,%1,%2,%3}, [%4];" : "=r"(v.x), "=r"(v.y), "=r"(v.z), "=r"(v.w) : "l"(p) : "memory"); return v; }
__device__ __forceinline__ uint4 lds4(uint32_t a) { uint4 v; asm volatile("ld.shared.v4.u32 {%0,%1,%2,%3}, [%4];" : "=r"(v.x), "=r"(v.y), "=r"(v.z), "=r"(v.w) : "r"(a) : "memory"); return v; }
__device__ __forceinline__ float2 lds2f(uint32_t a) { float2 v; asm volatile("ld.shared.v2.f32 {%0,%1}, [%2];" : "=f"(v.x), "=f"(v.y) : "r"(a) : "memory"); return v; }
__device__ __forceinline__ uint32_t lds1(uint32_t a) { uint32_t v; asm volatile("ld.shared.u32 %0, [%1];" : "=r"(v) : "r"(a) : "memory"); return v; }
__device__ __forceinline__ void sts4(uint32_t a, uint4 v) { asm volatile("st.shared.v4.u32 [%0], {%1,%2,%3,%4};" ::"r"(a), "r"(v.x), "r"(v.y), "r"(v.z), "r"(v.w) : "memory"); }
__device__ __forceinline__ void sts1(uint32_t a, uint32_t v) { asm volatile("st.shared.u32 [%0], %1;" ::"r"(a), "r"(v) : "memory"); }
__device__ __forceinline__ void stsm4(uint32_t a, uint32_t r0, uint32_t r1, uint32_t r2, uint32_t r3) {
    asm volatile("stmatrix.sync.aligned.m8n8.x4.shared.b16 [%0], {%1,%2,%3,%4};" ::"r"(a), "r"(r0), "r"(r1), "r"(r2), "r"(r3));
}
__device__ __forceinline__ uint32_t pack2(float lo, float hi) { uint32_t r; asm("cvt.rn.bf16x2.f32 %0, %1, %2;" : "=r"(r) : "f"(hi), "f"(lo)); return r; }
__device__ __forceinline__ uint32_t pack2_relu(float lo, float hi) { uint32_t r; asm("cvt.rn.relu.bf16x2.f32 %0, %1, %2;" : "=r"(r) : "f"(hi), "f"(lo)); return r; }
__device__ __forceinline__ uint32_t hfma2(uint32_t a, uint32_t b, uint32_t c) { uint32_t r; asm("fma.rn.bf16x2 %0, %1, %2, %3;" : "=r"(r) : "r"(a), "r"(b), "r"(c)); return r; }
__device__ __forceinline__ uint32_t hmul2(uint32_t a, uint32_t b) { uint32_t r; asm("mul.rn.bf16x2 %0, %1, %2;" : "=r"(r) : "r"(a), "r"(b)); return r; }
__device__ __forceinline__ float bf_lo(uint32_t v) { return __uint_as_float(v << 16); }
__device__ __forceinline__ float bf_hi(uint32_t v) { return __uint_as_float(v & 0xFFFF0000u); }
__device__ __forceinline__ float bf_round(float v) { return bf_lo(pack2(v, 0.f)); }
__device__ __forceinline__ float ex2(float x) { float r; asm("ex2.approx.ftz.f32 %0, %1;" : "=f"(r) : "f"(x)); return r; }
__device__ __forceinline__ void mma16816(float* d, uint32_t a0, uint32_t a1, uint32_t a2, uint32_t a3, uint32_t b0, uint32_t b1) {
    asm("mma.sync.aligned.m16n8k16.row.col.f32.bf16.bf16.f32 {%0,%1,%2,%3}, {%4,%5,%6,%7}, {%8,%9}, {%0,%1,%2,%3};"
        : "+f"(d[0]), "+f"(d[1]), "+f"(d[2]), "+f"(d[3]) : "r"(a0), "r"(a1), "r"(a2), "r"(a3), "r"(b0), "r"(b1));
}
__device__ __forceinline__ void mma1688(float* d, uint32_t a0, uint32_t a1, uint32_t b0) {
    asm("mma.sync.aligned.m16n8k8.row.col.f32.bf16.bf16.f32 {%0,%1,%2,%3}, {%4,%5}, {%6}, {%0,%1,%2,%3};"
        : "+f"(d[0]), "+f"(d[1]), "+f"(d[2]), "+f"(d[3]) : "r"(a0), "r"(a1), "r"(b0));
}
__device__ __forceinline__ void ldsm4(uint32_t a, uint32_t* r) {
    asm volatile("ldmatrix.sync.aligned.m8n8.x4.shared.b16 {%0,%1,%2,%3}, [%4];" : "=r"(r[0]), "=r"(r[1]), "=r"(r[2]), "=r"(r[3]) : "r"(a));
}
__device__ __forceinline__ void ldsm4t(uint32_t a, uint32_t* r) {
    asm volatile("ldmatrix.sync.aligned.m8n8.x4.trans.shared.b16 {%0,%1,%2,%3}, [%4];" : "=r"(r[0]), "=r"(r[1]), "=r"(r[2]), "=r"(r[3]) : "r"(a));
}
__device__ __forceinline__ uint32_t nz(uint32_t v) { uint32_t r; asm("max.u32 %0, %1, 1;" : "=r"(r) : "r"(v)); return r; }
__device__ __forceinline__ float rcp(float x) { float r; asm("rcp.approx.ftz.f32 %0, %1;" : "=f"(r) : "f"(x)); return r; }
__device__ __forceinline__ uint2 ld_relaxed2(const void* p) { uint2 v; asm volatile("ld.relaxed.gpu.global.v2.u32 {%0,%1}, [%2];" : "=r"(v.x), "=r"(v.y) : "l"(p) : "memory"); return v; }
__host__ __device__ constexpr uint64_t dconst(uint32_t lbo, uint32_t sbo, uint32_t swz) {
    return ((uint64_t)(lbo >> 4) << 16) | ((uint64_t)(sbo >> 4) << 32) | ((uint64_t)swz << 62);
}
__device__ __forceinline__ uint32_t mkdesc(uint32_t addr, uint64_t c) { return (uint32_t)c | ((addr & 0x3FFFF) >> 4); }
#define WG_FENCE() asm volatile("wgmma.fence.sync.aligned;" ::: "memory")
#define WG_COMMIT() asm volatile("wgmma.commit_group.sync.aligned;" ::: "memory")
#define WG_WAIT(n) asm volatile("wgmma.wait_group.sync.aligned %0;" ::"n"(n) : "memory")
template <int N> __device__ __forceinline__ void reg_fence(float* d) {
#pragma unroll
    for (int i = 0; i < N; i++) asm volatile("" : "+f"(d[i])::"memory");
}
template <int N> __device__ __forceinline__ void reg_def(float* d) {
#pragma unroll
    for (int i = 0; i < N; i++) asm volatile("" : "=f"(d[i]));
}
template <int N> __device__ __forceinline__ void reg_def(uint32_t* d) {
#pragma unroll
    for (int i = 0; i < N; i++) asm volatile("" : "=r"(d[i]));
}
__device__ __forceinline__ void wait_flags(const uint32_t* p, uint32_t target, uint32_t mask) {
    int n = 0;
    while (~__ballot_sync(~0u, ld_relaxed(p) == target) & mask) { if (++n > SPIN_LIMIT) __trap(); }
    asm volatile("fence.acquire.gpu;" ::: "memory");
}
__device__ __forceinline__ float silu_bf(uint32_t cbits) {
    const float c = __uint_as_float(cbits << 16);
    return bf_round(__fdividef(c, 1.f + fminf(ex2(-1.4426950408889634f * c), 1e30f)));
}
__device__ __forceinline__ void gemv_part(uint32_t wmbuf, int wp, int lane) {
    const uint32_t wa = wmbuf + wp * 512 + (8 * (lane >> 4) + (lane & 7)) * 32 + ((lane >> 3) & 1) * 16;
    float d[4] = {};
#pragma unroll
    for (int i = 0; i < 4; i++) {
        uint32_t A[4];
        const float2 v = lds2f(wmbuf + 28672 + (wp + 8 * i) * 32 + (lane & 3) * 8);
        ldsm4t(wa + (i < 3 || wp < 4 ? i : 0) * 4096, A);
        mma16816(d, A[0], A[1], A[2], A[3], __float_as_uint(v.x), __float_as_uint(v.y));
    }
    if ((lane & 3) == 0) {
        sts1(wmbuf + 29696 + (wp * 16 + (lane >> 2)) * 4, __float_as_uint(d[0]));
        sts1(wmbuf + 29696 + (wp * 16 + 8 + (lane >> 2)) * 4, __float_as_uint(d[2]));
    }
}
__device__ __forceinline__ uint32_t mod_word(float v, int col, uint32_t target) {
    v = bf_round(v);
    if ((col >= DM && col < 2 * DM) || (col >= 4 * DM && col < 5 * DM)) v += 1.f;
    return (pack2(v, 0.f) << 16) | (target & 0xFFFFu);
}
__device__ __forceinline__ const uint4* mod_src(int i, int r, int j, bool p2) {
    i = min(i, p2 ? 251 : 223);
    return (const uint4*)g_mod + (r & 7) * (6 * DM / 4) + (i < 224 ? (p2 ? 336 : 0) + i : (i < 238 ? 14 * j + i : 14 * j + i + 322));
}
__device__ __forceinline__ void mod_store(uint32_t sb, uint4 v, const uint4* src, int i) {
    const uint32_t tag = lds1(sb + M_EPOCH) + 1;
    while (__any_sync(~0u, (((v.x ^ tag) | (v.y ^ tag) | (v.z ^ tag) | (v.w ^ tag)) & 0xFFFFu) != 0u)) v = ld_relaxed4(src);
    if (i < 224) {
        const int isc = i >= 112, c4 = i - 112 * isc;
        const uint32_t a = sb + M_ST + (c4 >> 2) * 64 + (c4 & 1) * 32 + (c4 & 2) * 4 + (isc ? 0 : 4);
        sts1(a, __byte_perm(v.x, v.y, 0x7632));
        sts1(a + 16, __byte_perm(v.z, v.w, 0x7632));
    } else if (i < 252) {
        sts4(sb + M_G + (i - 224) * 16, make_uint4(v.x & 0xFFFF0000u, v.y & 0xFFFF0000u, v.z & 0xFFFF0000u, v.w & 0xFFFF0000u));
    }
}
__device__ __forceinline__ int pass_f(int fs, int ps) { return 224 * fs + ((fs & 1) ? (ps == 0 ? 96 : ps == 1 ? 32 : 0) : (ps == 0 ? 0 : ps == 1 ? 128 : 192)); }
__device__ __forceinline__ constexpr uint32_t slot_off(int l) { return l * 16384 + (l >= 10 ? 8192 : 0); }
constexpr uint64_t RING_ORDER = 0x6543C92B81A70ull;
constexpr uint32_t Y_XCH = 49152;
__device__ __forceinline__ constexpr int g1_slot(int s) { return s % 7; }
__device__ __noinline__ void x1_fix(const uint32_t* g, uint32_t sa, int s) {
#pragma unroll 1
    for (int k = 4 * s; k < 4 * s + 4;) {
        const uint4 v = ld_relaxed4((const uint4*)(g + k * 256));
        sts4(sa + k * 1024, v);
        k += 2 * __all_sync(~0u, min(min(v.x, v.y), min(v.z, v.w)) != 0u);
    }
    __syncwarp();
}
struct LnRow { uint32_t nm, hi, lo; };
__device__ __forceinline__ LnRow ln_coeffs(float mean, float msq) {
    const float var = bf_round(fmaxf(msq - mean * mean, 0.f));
    float sd;
    asm("sqrt.approx.f32 %0, %1;" : "=f"(sd) : "f"(bf_round(var + 1e-5f)));
    const float inv = rcp(bf_round(sd)), hi = bf_round(inv);
    LnRow c;
    c.nm = pack2(-bf_round(mean) * hi, -bf_round(mean) * hi);
    c.hi = pack2(hi, hi);
    c.lo = pack2(inv - hi, inv - hi);
    return c;
}
__device__ __forceinline__ uint32_t ln_norm(uint32_t x, const LnRow& c) {
    return hfma2(x, c.hi, c.nm);
}
__device__ __forceinline__ uint32_t ln_mod(uint32_t y, uint32_t sc, uint32_t sh) {
    return hfma2(y, sc, sh);
}

#define LOADW bulk_e(dst, g_wd + (size_t)((f >> 5) * 4 + nq) * 1792, 7168, bar);
template <int sec> __device__ __forceinline__ void ring_loader(const Params& p, uint32_t sb_, int r_, int j_, int lane) {
    const uint32_t sb = opaque(sb_);
    const int r = opaque(r_), j = opaque(j_), nq = j >> 1, fs = 4 * (j & 1) + nq;
    const int fa = pass_f(fs, 0), fb = pass_f(fs, 1), fc = pass_f(fs, 2);
    const uint32_t* h2src = (const uint32_t*)__shfl_sync(~0u, (unsigned long long)(p.actb + (size_t)r * RB_WORDS + RB_H2), 0);
    const CUtensorMap* gmap = (const CUtensorMap*)__shfl_sync(~0u, (unsigned long long)(&p.ga + sec), 0);
#define BAR(i) (sb + M_BAR + 8 * (i))
#define kh (j & 1)
            int sl = 0;
#pragma unroll 1
            for (int s = 0; s < 21; s++) {
                if (s == 7) { wait_flags(g_flag + (8 * r + j) * 192 + 96 + lane, lds1(sb + M_EPOCH) + 1, 0xFFFFu); fence_async_global(); }
                if (s >= 1 && s < 6) mbar_wait(BAR(B_FULL + s - 1), 0);
                mbar_wait(BAR(B_EMPTY + sl), s >= 7 && s < 14);
                expect_e(BAR(B_FULL + sl), 8192);
                tma3_e(sb + slot_off(sl) + sec * 8192, gmap + (s < 14 ? 0 : 2), 0, s < 14 ? 32 * s : 64 * sl, (s < 14 ? fa : fb) >> 6, BAR(B_FULL + sl));
                sl = sl == 6 ? 0 : sl + 1;
            }
#pragma unroll 1
            for (int s = 0; s < 7; s++) {
                const uint32_t bar = BAR(B_FULL + s);
                uint32_t dst = sb + slot_off(s) + sec * 4096;
                mbar_wait(BAR(B_EMPTY + s), 1);
                expect_e(bar, s < 3 ? 8192 : s > 3 ? 7168 : sec ? 4096 : 4096 + 7168);
                if (s < 4) tma3_e(dst, gmap + 4, 0, 128 * s, fc >> 5, bar);
                if (s < 3) tma3_e(dst + 8192, gmap + 4, 0, 128 * s + 64, fc >> 5, bar);
                else if (s > 3 || !sec) {
                    const int f = s == 3 ? fc : (s < 6 ? fa + 64 * (s - 4) : fb) + 32 * sec;
                    dst = sb + slot_off(s) + (s == 3 || sec ? 8192 : 0);
                    LOADW
                }
            }
            if (!sec) PROFH(3);
            if (sec) asm volatile("prefetch.tensormap [%0];" ::"l"(&p.om) : "memory");
            int e = 0;
#pragma unroll 1
            for (int grp = 0; grp < 9; grp++) {
                const int ps = grp >= 6 ? 2 : grp >= 3 ? 1 : 0;
                int sidx = grp - 3 * ps;
                if (sec && sidx == 0) { mbar_wait(BAR(B_HRDY + ps), 0); fence_async_global(); }
                sidx += sidx >= nq;
                int f = pass_f(4 * kh + sidx, ps);
#pragma unroll 1
                for (int k = 4 >> ps; k > 0; k--, e++, f += 32) {
                    sl = (RING_ORDER >> (4 * (e < 13 ? e : e - 13))) & 15;
                    const uint32_t dst = sb + slot_off(sl), bar = BAR(B_FULL + sl);
                    mbar_wait(BAR(B_EMPTY + sl), e >= 13);
                    if (e >= WIN) mbar_wait(BAR(B_FULL + ((RING_ORDER >> (4 * (e - WIN < 13 ? e - WIN : e - WIN - 13))) & 15)), e - WIN >= 13);
                    expect_e(bar, sec ? 8192 : 7168);
                    if (!sec) { LOADW }
                    else bulk_e(dst + 8192, h2src + f * 64, 8192, bar);
                }
            }
            if (!sec) PROFH(4);
}

#define PROF_PARAMS
#define PROF_ARGS
__device__ __noinline__ void helper_late(const Params& p, int r_, int j_, int warp_ PROF_PARAMS) {
    extern __shared__ __align__(1024) unsigned char smem[];
    const uint32_t sb = (uint32_t)__cvta_generic_to_shared(smem);
    const int r = opaque(r_), j = opaque(j_), warp = opaque(warp_), nq = j >> 1, b = 8 * r + j;
    uint32_t* const act = (uint32_t*)__shfl_sync(~0u, (unsigned long long)(p.actb + (size_t)r * RB_WORDS), 0);
    {
        const int lane = fresh_tid() & 31;
        const uint32_t target = lds1(sb + M_EPOCH) + 1;
        if (warp == 8) { expect_e(BAR(B_XCH), 7168); expect_e(BAR(B_XCH + 1), 7168); }
            if (warp == 9) {
#pragma unroll 1
                for (int kv = 0; kv < 2; kv++) {
                    mbar_wait(BAR(B_PUB + kv), 0);
                    wait_flags(g_flag + b * 192 + lane, target, (r >= 2 ? 6u : r == 1 ? 2u : 0u) << (8 * kv));
                    fence_async_global();
                    const uint32_t dst = sb + OFF_Y + (kv ? Y_VR : Y_K);
                    expect_e(BAR(B_KRFULL + kv), r >= 2 ? 28672 : r == 1 ? 14336 : 0);
                    if (r >= 2) bulk_e(dst, act - 2 * RB_WORDS + RB_KV + j * 7168 + kv * 3584, 14336, BAR(B_KRFULL + kv));
                    if (r >= 1) bulk_e(dst + 14336, act - RB_WORDS + RB_KV + j * 7168 + kv * 3584, 14336, BAR(B_KRFULL + kv));
                    if (kv == 0) { PROFH(8); }
                }
            } else if (warp == 8) {
                uint4 v[8];
                mbar_wait(BAR(B_WOFULL), 0);
#pragma unroll
                for (int k = 0; k < 8; k++) v[k] = ld_relaxed4(mod_src(lane + 32 * k, r, j, true));
#pragma unroll
                for (int k = 0; k < 8; k++) mod_store(sb, v[k], mod_src(lane + 32 * k, r, j, true), lane + 32 * k);
                warp_arrive(BAR(B_MOD1));
            } else if (warp == 11) {
                if (kh == 1 && r < 14) {
                    const uint32_t wmbuf = sb + OFF_X + HALF;
                    const int mcol = 2 * DM + 32 * (4 * r + nq);
                    mbar_wait(BAR(B_XFREE), 0);
                    tma3_e(wmbuf, &p.wm2, mcol, 0, 0, BAR(B_WMFULL));
                    tma3_e(wmbuf + 14336, &p.wm2, mcol, 224, 0, BAR(B_WMFULL));
#pragma unroll 1
                    for (int wd = lane; wd < 224; wd += 32) {
                        const uint32_t cb = __ldg((const uint32_t*)p.c + wd);
                        sts1(wmbuf + 28672 + (wd >> 3) * 32 + (wd & 3) * 8 + (wd & 4), pack2(silu_bf(cb & 0xFFFFu), silu_bf(cb >> 16)));
                    }
                    __syncwarp();
                    mbar_wait(BAR(B_WMFULL), 0);
                    const uint32_t wa = wmbuf + (8 * (lane >> 4) + (lane & 7)) * 64 + ((lane >> 3) & 1) * 16;
                    float d[2][4] = {};
#pragma unroll 4
                    for (int ks = 0; ks < 28; ks++) {
                        uint32_t A[8];
                        ldsm4t(wa + ks * 1024, A); ldsm4t(wa + ks * 1024 + 32, A + 4);
                        const float2 v = lds2f(wmbuf + 28672 + ks * 32 + (lane & 3) * 8);
                        mma16816(d[0], A[0], A[1], A[2], A[3], __float_as_uint(v.x), __float_as_uint(v.y));
                        mma16816(d[1], A[4], A[5], A[6], A[7], __float_as_uint(v.x), __float_as_uint(v.y));
                    }
                    const int q = lane & 3, col = mcol + 8 * q + (lane >> 2);
                    const uint32_t word = mod_word(q == 0 ? d[0][0] : q == 1 ? d[0][2] : q == 2 ? d[1][0] : d[1][2], col, target);
#pragma unroll
                    for (int i = 0; i < 8; i++) st_relaxed(g_mod + i * 6 * DM + col, word);
                }
                warp_arrive(BAR(B_WMFREE));
                mbar_wait(BAR(B_VRFULL), 0);
                l2_prefetch_e((const char*)p.wg + (size_t)b * 12544, 12544);
                l2_prefetch_e((const char*)p.wu + (size_t)b * 12544, 12544);
#pragma unroll 1
                for (int k = 0; k < (r < 12 ? 2 : 1); k++) {
                    const int u = 28 * kh + r + 16 * k;
                    expect_e(BAR(B_XFULL + k), 7168);
                    tma3_e(sb + OFF_Y + 102400, &p.dn, 0, 32 * u, 7 * j, BAR(B_XFULL + k));
                    tma3_e(sb + OFF_Y + 102400 + 3584, &p.dn, 0, 32 * u, 7 * (j ^ 1), BAR(B_XFULL + k));
                    mbar_wait(BAR(B_XFULL + k), 1);
                    asm volatile("{\n.reg .pred p;\nelect.sync _|p, 0xffffffff;\n@p cp.async.bulk.global.shared::cta.bulk_group [%0], [%1], 7168;\n"
                                 "cp.async.bulk.commit_group;\ncp.async.bulk.wait_group 0;\n}" ::"l"(g_wd + (size_t)(u * 4 + nq) * 1792), "r"(sb + OFF_Y + 102400) : "memory");
                    __syncwarp();
                }
                warp_arrive(BAR(B_FULLK));
                fence_gpu();
                if (lane < 16) st_relaxed(g_flag + (8 * lane + j) * 192 + 96 + r, target);
            }
        if (warp == 8 || warp == 11) {
            const int sec = warp == 11;
            if (sec) ring_loader<1>(p, sb, r, j, lane); else ring_loader<0>(p, sb, r, j, lane);
            mbar_wait(BAR(B_DONE), 0);
        } else if (warp == 9) {
#pragma unroll
            for (int ev = 0; ev < 4; ev++) { expect_e(BAR(B_GFULL + ev), ev < 2 ? HALF / 2 : 16384); expect_e(BAR(B_XFULL + 2 + ev), ev < 2 ? HALF / 2 : HALF - 16384); }
            mbar_wait(BAR(B_PUB + 2), 0);
            expect_e(BAR(B_FULLV), 4096); expect_e(BAR(B_FULLQ), 4096);
            const int par = (target - 1) & 1;
#pragma unroll 1
            for (int ev = 0; ev < 4; ev++) {
                if (ev == 1) { mbar_wait(BAR(B_FULLK), 1); mbar_wait(BAR(B_PUB + 3), 0); }
                const int tile = (ev & 1) + (ev >> 1) * par * 2;
                const uint32_t dst = sb + (ev == 0 ? OFF_X : OFF_Y + (ev & 1) * HALF), first = ev < 2 ? HALF / 2 : 16384;
                const char* src = (const char*)(act + RB_O + ((ev >> 1) * 2 + tile) * 14336);
                wait_flags(g_flag + b * 192 + (ev < 2 ? 32 : 64 + 32 * ev) + lane, target, ev < 2 ? 0xFFu << (8 * ev) : ~0u);
                fence_async_global();
                if (ev >= 2) bulk_e(sb + OFF_X + X_STAT + (ev & 1) * 49152, act + RB_ST + tile * 1024, 4096, BAR(B_FULLV + (ev & 1)));
                bulk_e(dst, src, first, BAR(B_GFULL + ev));
                bulk_e(dst + first, src + first, HALF - first, BAR(B_XFULL + 2 + ev));
                if (ev) PROFH(4 + ev);
            }
            mbar_wait(BAR(B_XFULL + 5), 1);
#pragma unroll 1
            for (int hf = 0; hf < 2; hf++) {
                const int tile = (par ^ 1) * 2 + hf;
                uint4* xz = (uint4*)(act + RB_X1 + tile * 14336 + j * 1792) + lane;
#pragma unroll
                for (int i = 0; i < 14; i++) xz[i * 32] = make_uint4(0, 0, 0, 0);
                ((uint4*)(act + RB_ST + (tile * 8 + j) * 128))[lane] = make_uint4(0, 0, 0, 0);
            }
#pragma unroll 1
            for (int ps = 0; ps < 3; ps++) {
                mbar_wait(BAR(B_PUB + 6 + ps), 0);
                if (ps == 1) {
                    fence_gpu();
                    if (lane < 8) st_relaxed(g_flag + (8 * r + lane) * 192 + 72 + j, target);
                }
                wait_flags(g_flag + b * 192 + 64 + lane, target, (0x55u << kh) << (8 * ps));
                warp_arrive(BAR(B_HRDY + ps));
                PROFH(9 + ps);
            }
        } else {
#pragma unroll 1
            for (int k = 0; k < 9; k++) {
                if (k == 4 || k == 5 || k == 7) continue;
                uint32_t* fp = k < 2 ? g_flag + (b + 8 * lane) * 192 + k * 8 + lane : g_flag + (8 * r + lane) * 192 + 16 + k * 8 + j;
                mbar_wait(BAR(B_PUB + k), 0);
                fence_gpu();
                if (k < 2 ? (lane == 1 || lane == 2) : lane < 8) st_relaxed(fp, target);
                if (k >= 3 && k <= 5) PROFH(k - 3);
            }
        }
    }
}

__global__ void __cluster_dims__(2, 1, 1) __launch_bounds__(384, 1) fused_block_kernel(const __grid_constant__ Params p) {
    extern __shared__ __align__(1024) unsigned char smem[];
    const uint32_t sb = (uint32_t)__cvta_generic_to_shared(smem);
    const int tid = threadIdx.x, lane = tid & 31, warp = __shfl_sync(~0u, tid >> 5, 0);
    const int m = blockIdx.x >> 1;
    int r, nq;
    if (m < 4) { r = 15; nq = m; }
    else if (m < 36) { r = (m - 4) & 7; nq = (m - 4) >> 3; }
    else { nq = (m - 36) / 7; r = m - 28 - 7 * nq; }
    const int j = opaque(2 * nq + (blockIdx.x & 1)), b = 8 * r + j, fs = 4 * kh + nq;
#define act (p.actb + (size_t)r * RB_WORDS)
    uint32_t ticket = 0;
    if (tid == 288) ticket = atomicAdd(&g_ticket, 1u);
    if (warp == 10 && blockIdx.x < 112) {
#pragma unroll
        for (int i = 0; i < 4; i++) l2_prefetch_e(p.wmod + (size_t)(4 * blockIdx.x + i) * (6 * DM), 4 * DM);
    }
    if (warp == 11) l2_prefetch_e((const char*)p.x + (size_t)blockIdx.x * 14336, 14336);
    if (lane == 0 && warp < 9 && warp != 6 && warp != 7) {
        const int i0 = warp == 8 ? 0 : 8 + 8 * warp, cnt = warp == 0 || warp == 8 ? 1 : warp < 3 ? 2 : 8;
#pragma unroll
        for (int k = 0; k < 8; k++) if (i0 + k != B_WMFULL) mbar_init(BAR(i0 + k), cnt);
        if (warp == 8) mbar_init(BAR(B_WMFULL), 1);
        asm volatile("fence.mbarrier_init.release.cluster;" ::: "memory");
        fence_async_smem();
    }

    if (warp >= 8) {
        const int lane = fresh_tid() & 31;
        const bool early = kh == 0, gemv = r < 14;
        const int mcol = early ? 16 * (4 * r + nq) : 2 * DM + 32 * (4 * r + nq);
        const uint32_t wmbuf = sb + OFF_Y + HALF;
        if (warp == 8) {
            __syncwarp();
            expect_e(BAR(B_WMFULL), gemv ? 28672 >> early : 0);
            if (early && gemv) { tma3_e(wmbuf, &p.wm, mcol, 0, 0, BAR(B_WMFULL)); tma3_e(wmbuf + 7168, &p.wm, mcol, 224, 0, BAR(B_WMFULL)); }
#pragma unroll
            for (int kb = 0; kb < 7; kb++) {
                expect_e(BAR(B_XFULL + kb), 16384);
                tma3_e(sb + OFF_X + kb * 16384, &p.xm, 64 * kb, 128 * r, 0, BAR(B_XFULL + kb));
            }
        }
        asm volatile("setmaxnreg.dec.sync.aligned.u32 56;");
        if (warp == 10) {
#pragma unroll
            for (int i = 56; i < 64; i++) init_e(BAR(i), 1);
            fence_async_smem();
        }
        bar_arrive(0, 384);
        asm volatile("barrier.cluster.arrive.relaxed.aligned;" ::: "memory");
        if (warp == 8) {
            mbar_wait(BAR(B_XFULL), 0);
            l2_prefetch_e((const char*)p.wqkv + (size_t)b * 9408, 9408);
#pragma unroll 1
            for (int mt = 0; mt < 4; mt++) {
                if (mt == 1) bar_sync(9, 384);
                if (mt == 3) mbar_wait(BAR(B_WMFREE), 0);
                if (mt == 1 && early) mbar_wait(BAR(B_WMFREE), 0);
                if (mt) mbar_wait(BAR(mt == 1 ? B_FULLK : mt == 2 ? B_MOD1 : B_VRFULL), 0);
                const uint32_t bar = BAR(mt == 3 ? B_WOFULL : B_FULLK + mt), dst = sb + (mt < 2 ? OFF_Y : OFF_X) + (mt & 1) * HALF;
                const int c0 = (mt < 2 ? DM + DM * mt : 0) + 56 * j - 8 * kh;
                expect_e(bar, HALF);
                tma3_e(dst, mt == 3 ? &p.wo : &p.qkv, c0, 0, 0, bar);
                tma3_e(dst + HALF / 2, mt == 3 ? &p.wo : &p.qkv, c0, 224, 0, bar);
            }
        } else {
            if (warp == 10 && lane < 13) asm volatile("prefetch.tensormap [%0];" ::"l"(&p.wm + lane) : "memory");
            if (tid == 288) sts1(sb + M_EPOCH, ticket / NCTA);
            bar_sync(9, 384);
            if (warp == 9 && lane < 8) mbar_arrive(BAR(B_EPOCH));
            if (warp == 11 && early) {
                const uint32_t target = lds1(sb + M_EPOCH) + 1;
                mbar_wait(BAR(B_GEMV), 0);
                float sum = 0.f;
#pragma unroll
                for (int i = 0; i < 8; i++) sum += *(const float*)(smem + OFF_Y + HALF + 29696 + (i * 16 + (lane & 15)) * 4);
                uint32_t* mg = g_mod + mcol + (lane & 15) + (lane >> 4) * 4 * 6 * DM;
                const uint32_t word = mod_word(sum, mcol, target);
                if (gemv) { st_relaxed(mg, word); st_relaxed(mg + 6 * DM, word); st_relaxed(mg + 12 * DM, word); st_relaxed(mg + 18 * DM, word); }
            }
        }
    }
    if (warp < 8) {
        const int w = (warp >> 2) ^ 1, wi = warp & 3;
#define COORDS const int t = fresh_tid() & 127, lane = t & 31, q = lane & 3, lr = lane >> 2, ra = 64 * w + 16 * wi + lr; \
        const uint32_t lx = (lane >> 4) ^ (lane & 7), mrow = (64 * w + 16 * wi + ((lane >> 3) & 1) * 8 + (lane & 7)) * 128; \
        (void)q; (void)lr; (void)ra; (void)lx; (void)mrow;
#define WAIT(i, par) mbar_wait_c(BAR(i), par)
        constexpr uint64_t DB128 = dconst(4096, 1024, 1);
        {
            const int wd = fresh_tid();
            const uint32_t cb = wd < 224 ? __ldg((const uint32_t*)p.c + wd) : 0u;
            sts1(sb + OFF_Y + HALF + 28672 + (wd >> 3) * 32 + (wd & 3) * 8 + (wd & 4), pack2(silu_bf(cb & 0xFFFFu), silu_bf(cb >> 16)));
        }
        bar_arrive(9, 384);
        bar_sync(0, 384);
        asm volatile("barrier.cluster.arrive.relaxed.aligned;" ::: "memory");
        asm volatile("setmaxnreg.inc.sync.aligned.u32 224;");
        PROFC(0);
        uint32_t xr[16];
        {
            COORDS
            uint32_t h[112];
            LnRow ca, cb;
            const int mi = min(128 * w + t, 223);
            const uint4* msrc = mod_src(mi, r, j, false);
            uint4 mv;
            {
                float ds[4] = {}, da[2][4] = {}, db[2][4] = {};
                const uint32_t ONE2 = 0x3F803F80u;
#pragma unroll
                for (int kb = 0; kb < 7; kb++) {
                    if (kb == 0 && kh == 0) { WAIT(B_WMFULL, 0); gemv_part(sb + OFF_Y + HALF, warp, lane); warp_arrive(BAR(B_GEMV)); }
                    WAIT(B_XFULL + kb, 0);
#pragma unroll
                    for (int k4 = 0; k4 < 4; k4++) ldsm4(sb + OFF_X + mrow + kb * 16384 + (((2 * k4) ^ lx) << 4), h + 16 * kb + 4 * k4);
#pragma unroll
                    for (int k4 = 0; k4 < 4; k4++) {
                        const uint32_t* f = h + 16 * kb + 4 * k4;
                        mma16816(ds, f[0], f[1], f[2], f[3], ONE2, ONE2);
                        mma1688(da[0], f[0], f[1], f[0]); mma1688(db[0], f[0], f[1], f[1]);
                        mma1688(da[1], f[2], f[3], f[2]); mma1688(db[1], f[2], f[3], f[3]);
                    }
                }
#pragma unroll
                for (int i = 0; i < 4; i++) {
                    const int ch = 7 * j + 2 * i + (lane >> 4);
                    ldsm4(sb + OFF_X + mrow + (ch >> 3) * 16384 + (((ch ^ lane) & 7) << 4), xr + 4 * i);
                }
                mv = ld_relaxed4(msrc);
                warp_arrive(BAR(B_XFREE));
                float qa = (lr & 1) ? da[0][1] + da[1][1] : da[0][0] + da[1][0];
                float qb = (lr & 1) ? db[0][3] + db[1][3] : db[0][2] + db[1][2];
                const int src = (lane & ~3) | (lr >> 1);
                qa = __shfl_sync(~0u, qa, src);
                qb = __shfl_sync(~0u, qb, src);
                ca = ln_coeffs(ds[0] * (1.f / DM), qa * (1.f / DM));
                cb = ln_coeffs(ds[2] * (1.f / DM), qb * (1.f / DM));
#pragma unroll
                for (int i = 0; i < 4 * NPRE; i += 2) { h[i] = ln_norm(h[i], ca); h[i + 1] = ln_norm(h[i + 1], cb); }
            }
            PROFC(1);
            {
                float ak[28], av[28], aq[28];
                uint32_t kp[14], vp[14];
                const uint64_t bq0 = (DB128 & ~0xFFFFFFFFull) | (mkdesc(sb + OFF_X, DB128) + kh), bk0 = bq0 + (OFF_Y >> 4), bv0 = bk0 + (HALF >> 4);
                uint32_t* kvg = act + RB_KV + j * 7168 + (8 * w + 2 * wi) * 224 + lane;
                WAIT(B_EPOCH, 0);
                mod_store(sb, mv, msrc, mi);
                bar_sync(3, 256);
                if (warp == 0) warp_arrive(BAR(B_MOD1));
                WAIT(B_FULLK, 0);
                PROFC(2);
                reg_def<28>(ak);
#pragma unroll
                for (int g4 = 0; g4 < 4; g4++) {
#pragma unroll
                    for (int ks = 7 * g4; ks < 7 * g4 + 7; ks++) {
                        const uint4 st = *(const uint4*)(smem + M_ST + ks * 64 + q * 16);
                        if (ks >= NPRE) {
                            h[4 * ks] = ln_norm(h[4 * ks], ca); h[4 * ks + 1] = ln_norm(h[4 * ks + 1], cb);
                            h[4 * ks + 2] = ln_norm(h[4 * ks + 2], ca); h[4 * ks + 3] = ln_norm(h[4 * ks + 3], cb);
                        }
                        h[4 * ks] = ln_mod(h[4 * ks], st.x, st.y); h[4 * ks + 1] = ln_mod(h[4 * ks + 1], st.x, st.y);
                        h[4 * ks + 2] = ln_mod(h[4 * ks + 2], st.z, st.w); h[4 * ks + 3] = ln_mod(h[4 * ks + 3], st.z, st.w);
                    }
                    WG_FENCE();
#pragma unroll
                    for (int ks = 7 * g4; ks < 7 * g4 + 7; ks++) wgmma_rl_56(ak, h[4 * ks], h[4 * ks + 1], h[4 * ks + 2], h[4 * ks + 3], bk0 + ks * 128, ks != 0);
                }
                WG_COMMIT();
                PROFC(3);
                reg_def<28>(av);
                WG_WAIT(0);
                reg_fence<28>(ak);
#pragma unroll
                for (int g = 0; g < 7; g++) {
                    kp[2 * g] = pack2(ak[4 * g], ak[4 * g + 1]); kp[2 * g + 1] = pack2(ak[4 * g + 2], ak[4 * g + 3]);
                    kvg[g * 32] = kp[2 * g]; kvg[224 + g * 32] = kp[2 * g + 1];
                }
                warp_arrive(BAR(B_PUB));
                PROFC(4);
                WAIT(B_FULLV, 0);
                WG_FENCE();
#pragma unroll
                for (int ks = 0; ks < 28; ks++) wgmma_rl_56(av, h[4 * ks], h[4 * ks + 1], h[4 * ks + 2], h[4 * ks + 3], bv0 + ks * 128, ks != 0);
                WG_COMMIT();
                reg_def<28>(aq);
                WAIT(B_FULLQ, 0);
                WG_FENCE();
#pragma unroll
                for (int ks = 0; ks < VPRE; ks++) wgmma_rl_56(aq, h[4 * ks], h[4 * ks + 1], h[4 * ks + 2], h[4 * ks + 3], bq0 + ks * 128, ks != 0);
                WG_COMMIT();
                WG_WAIT(1);
                reg_fence<28>(av);
#pragma unroll
                for (int g = 0; g < 7; g++) {
                    vp[2 * g] = pack2(av[4 * g], av[4 * g + 1]); vp[2 * g + 1] = pack2(av[4 * g + 2], av[4 * g + 3]);
                    kvg[3584 + g * 32] = vp[2 * g]; kvg[3584 + 224 + g * 32] = vp[2 * g + 1];
                }
                warp_arrive(BAR(B_PUB + 1));
                PROFC(5);
                WG_FENCE();
#pragma unroll
                for (int ks = VPRE; ks < 28; ks++) wgmma_rl_56(aq, h[4 * ks], h[4 * ks + 1], h[4 * ks + 2], h[4 * ks + 3], bq0 + ks * 128, ks != 0);
                WG_COMMIT();
                WAIT(B_PUB + 1, 0);
                const uint32_t rg = 8 * w + 2 * wi + ((lane >> 3) & 1);
                const uint32_t ko = sb + OFF_Y + Y_KOWN + rg * 896 + (lane & 7) * 16, qo = sb + OFF_Y + Y_Q + rg * 1024 + (lane >> 4) * 128 + (lane & 7) * 16;
#pragma unroll
                for (int g = 0; g < 6; g += 2) {
                    stsm4(ko + (g + (lane >> 4)) * 128, kp[2 * g], kp[2 * g + 1], kp[2 * g + 2], kp[2 * g + 3]);
                    stsm4(ko + (Y_VOWN - Y_KOWN) + (g + (lane >> 4)) * 128, vp[2 * g], vp[2 * g + 1], vp[2 * g + 2], vp[2 * g + 3]);
                }
                stsm4(ko + (lane >> 4) * (Y_VOWN - Y_KOWN) + 6 * 128, kp[12], kp[13], vp[12], vp[13]);
                WG_WAIT(0);
                reg_fence<28>(aq);
                __syncwarp();
                if (lane < 3 && w == 1) mbar_arrive(BAR(B_EMPTY + lane));
                uint32_t qp[14];
#pragma unroll
                for (int i = 0; i < 14; i++) qp[i] = pack2(aq[2 * i], aq[2 * i + 1]);
                stsm4(qo, qp[0], qp[1], qp[2], qp[3]);
                stsm4(qo + 256, qp[4], qp[5], q < 2 ? qp[6] : 0u, q < 2 ? qp[7] : 0u);
                stsm4(qo + 512, q < 2 ? 0u : qp[6], q < 2 ? 0u : qp[7], qp[8], qp[9]);
                stsm4(qo + 768, qp[10], qp[11], qp[12], qp[13]);
                fence_async_smem();
                if (w == 0) { bar_arrive(4, 256); bar_sync(1, 128); } else { bar_arrive(5, 256); bar_sync(4, 256); }
            }
        }
        PROFC(6);
        WAIT(B_KRFULL, 0);
        PROFC(7);
        {
#pragma unroll 1
            for (int hf = 0; hf < 2; hf++) {
                COORDS
                if (hf > w) bar_sync(5, 256);
                float s[160];
                const float CS = 0.18898223650461361f * 1.4426950408889634f;
                const float NEG = __int_as_float(0xFF800000);
                constexpr uint64_t DQ = dconst(128, 1024, 0), DK = dconst(128, 896, 0);
                {
                    const uint32_t qd = mkdesc(sb + OFF_Y + Y_Q + hf * 8192 + w * 512, DQ), kd = mkdesc(sb + OFF_Y + Y_K + hf * 8 * 896 + w * 384, DK);
                    reg_def<160>(s);
                    WG_FENCE();
                    wgmma_sk_160<DQ, DK>(s, qd, kd, 0);
                    wgmma_sk_160<DQ, DK>(s, qd + 16, kd + 16, 1);
                    wgmma_sk_160<DQ, DK>(s + 80, qd, kd + 20 * 56, 0);
                    wgmma_sk_160<DQ, DK>(s + 80, qd + 16, kd + 20 * 56 + 16, 1);
                    WG_COMMIT();
                    WG_WAIT(0);
                    reg_fence<160>(s);
                }
                if (r < 2) {
                    const int pmin = 4 - 2 * r - hf;
#pragma unroll
                    for (int p4 = 0; p4 < 4; p4++)
                        if (p4 < pmin) {
#pragma unroll
                            for (int i = 0; i < 32; i++) asm volatile("mov.b32 %0, 0xFF800000;" : "=f"(s[32 * p4 + i]));
                        }
                }
                const bool c0 = 2 * q > lr, c1 = 2 * q + 1 > lr;
#pragma unroll
                for (int pp = 0; pp < 4; pp++) {
                    const bool me = pp == wi;
                    float* e = s + 8 * pp;
                    if (me && !c0) { e[0] = NEG; e[6] = NEG; }
                    if (me && !c1) { e[1] = NEG; e[7] = NEG; }
                    if (me) { e[2] = NEG; e[3] = NEG; }
                    e = s + 8 * (pp + 16);
                    if (me && c0) { e[0] = NEG; e[6] = NEG; }
                    if (me && c1) { e[1] = NEG; e[7] = NEG; }
                    if (me) { e[4] = NEG; e[5] = NEG; }
                }
#pragma unroll
                for (int i = 0; i < 24; i++) s[i] = (i >> 3) < wi ? s[136 + i] : s[i];
                int i0 = 0x80000000, i1 = 0x80000000, i2 = 0x80000000, i3 = 0x80000000;
#pragma unroll
                for (int pp = 0; pp < 17; pp++) {
                    const float* e = s + 8 * pp;
                    i0 = __vimax3_s32(i0, __float_as_int(e[0]), __float_as_int(e[1])); i1 = __vimax3_s32(i1, __float_as_int(e[2]), __float_as_int(e[3]));
                    i2 = __vimax3_s32(i2, __float_as_int(e[4]), __float_as_int(e[5])); i3 = __vimax3_s32(i3, __float_as_int(e[6]), __float_as_int(e[7]));
                }
                i0 = max(i0, i2); i1 = max(i1, i3);
                i0 = max(i0, __shfl_xor_sync(~0u, i0, 1)); i1 = max(i1, __shfl_xor_sync(~0u, i1, 1));
                i0 = max(i0, __shfl_xor_sync(~0u, i0, 2)); i1 = max(i1, __shfl_xor_sync(~0u, i1, 2));
                if (__any_sync(~0u, (i0 | i1) < 0)) {
                    uint32_t u0 = ~0u, u1 = ~0u, u2 = ~0u, u3 = ~0u;
#pragma unroll
                    for (int pp = 0; pp < 17; pp++) {
                        const float* e = s + 8 * pp;
                        u0 = __vimin3_u32(u0, __float_as_uint(e[0]), __float_as_uint(e[1])); u1 = __vimin3_u32(u1, __float_as_uint(e[2]), __float_as_uint(e[3]));
                        u2 = __vimin3_u32(u2, __float_as_uint(e[4]), __float_as_uint(e[5])); u3 = __vimin3_u32(u3, __float_as_uint(e[6]), __float_as_uint(e[7]));
                    }
                    u0 = min(u0, u2); u1 = min(u1, u3);
                    u0 = min(u0, __shfl_xor_sync(~0u, u0, 1)); u1 = min(u1, __shfl_xor_sync(~0u, u1, 1));
                    u0 = min(u0, __shfl_xor_sync(~0u, u0, 2)); u1 = min(u1, __shfl_xor_sync(~0u, u1, 2));
                    if (i0 < 0) i0 = u0;
                    if (i1 < 0) i1 = u1;
                }
                const float ma = __int_as_float(i0), mb = __int_as_float(i1);
                const float na = -ma * CS, nb = -mb * CS;
                PROFC(8 + 3 * hf);
                {
                    WAIT(B_VRFULL, 0);
                    float o[16] = {}, rs[4] = {};
                    const uint32_t va = sb + OFF_Y + Y_VR + (8 * hf + ((lane >> 3) & 1)) * 896 + (3 * w + (lane >> 4)) * 128 + (lane & 7) * 16;
                    constexpr uint32_t OWN = Y_VOWN - 32 * 896;
#pragma unroll
                    for (int pp = 0; pp < 17; pp++) {
                        uint32_t B[8];
                        const uint32_t v = va + pp * 1792 + (pp < 3 ? (pp < wi ? 17 * 1792 + OWN : 0) : pp == 16 ? OWN : pp >= 12 ? hf * OWN : 0);
                        ldsm4t(v, B); ldsm4t(v + 256, B + 4);
                        float e[8];
#pragma unroll
                        for (int i = 0; i < 8; i++) e[i] = ex2(fmaf(s[8 * pp + i], CS, (i & 2) ? nb : na));
                        const uint32_t p0 = pack2(e[0], e[1]), p1 = pack2(e[2], e[3]), p2 = pack2(e[4], e[5]), p3 = pack2(e[6], e[7]);
                        mma16816(rs, p0, p1, p2, p3, 0x3F803F80u, 0x3F803F80u);
#pragma unroll
                        for (int g = 0; g < 4; g++) mma16816(o + 4 * g, p0, p1, p2, p3, B[2 * g], B[2 * g + 1]);
                    }
                    PROFC(9 + 3 * hf);
                    const float ia = rcp(rs[0]), ib = rcp(rs[2]);
                    uint32_t* og = act + RB_O + hf * 14336 + (7 * j + 3 * w) * 256 + wi * 64 + lane;
#pragma unroll
                    for (int g = 0; g < 4; g++) {
                        if ((g == 3 - 3 * w) ? ((q >> 1) == w) : true) {
                            og[g * 256] = pack2(o[4 * g] * ia, o[4 * g + 1] * ia);
                            og[g * 256 + 32] = pack2(o[4 * g + 2] * ib, o[4 * g + 3] * ib);
                        }
                    }
                    warp_arrive(BAR(B_PUB + 2 + hf));
                    PROFC(10 + 3 * hf);
                }
            }
        }
        uint32_t x1p[14];
        COORDS
        constexpr uint64_t DT = dconst(1024, 128, 0);
        const uint32_t epoch = lds1(sb + M_EPOCH);
        const int tile = opaque((epoch & 1) * 2 + w);
        {
            float ac[28];
            const uint32_t ad = mkdesc(sb + (w ? OFF_Y + HALF : OFF_X), DT), bd = mkdesc(sb + OFF_X + HALF, DB128) + kh;
            WAIT(B_WOFULL, 0);
            WAIT(B_MOD1, 1);
            WAIT(B_GFULL + w, 0);
            PROFC(28);
            reg_def<28>(ac);
#pragma unroll 1
            for (int u = 0; u < 4; u++) {
                if (u == 2) WAIT(B_XFULL + 2 + w, 1);
                WG_FENCE();
#pragma unroll
                for (int i = 0; i < 7; i++) wgmma_ss_56<DT, DB128>(ac, ad + (7 * u + i) * 128, bd + (7 * u + i) * 128, (u | i) != 0);
            }
            WG_COMMIT();
            WG_WAIT(0);
            reg_fence<28>(ac);
            PROFC(14);
            __syncwarp();
            if (lane < 3) mbar_arrive(BAR(B_EMPTY + 4 - w + lane));
            if (lane < 3 && w == 0) mbar_arrive(BAR(B_EMPTY + lane));
            float ds[4] = {}, da[4] = {}, db[4] = {};
            uint32_t* xo = act + RB_X1 + tile * 14336 + 7 * j * 256 + wi * 64 + lane;
#pragma unroll
            for (int g = 0; g < 7; g++) {
                const float2 ga = *(const float2*)(smem + M_G + (8 * g + 2 * q) * 4);
                x1p[2 * g] = pack2(fmaf(ga.x, ac[4 * g], bf_lo(xr[2 * g])), fmaf(ga.y, ac[4 * g + 1], bf_hi(xr[2 * g])));
                x1p[2 * g + 1] = pack2(fmaf(ga.x, ac[4 * g + 2], bf_lo(xr[2 * g + 1])), fmaf(ga.y, ac[4 * g + 3], bf_hi(xr[2 * g + 1])));
                st_relaxed(xo + g * 256, nz(x1p[2 * g])); st_relaxed(xo + g * 256 + 32, nz(x1p[2 * g + 1]));
                mma1688(ds, x1p[2 * g], x1p[2 * g + 1], 0x3F803F80u);
                mma1688(da, x1p[2 * g], x1p[2 * g + 1], x1p[2 * g]);
                mma1688(db, x1p[2 * g], x1p[2 * g + 1], x1p[2 * g + 1]);
            }
            const int src = (lane & ~3) | (lr >> 1);
            const float qa = __shfl_sync(~0u, (lr & 1) ? da[1] : da[0], src), qb = __shfl_sync(~0u, (lr & 1) ? db[3] : db[2], src);
            const float kk = (q & 1) ? ((q & 2) ? qb : qa) : ((q & 2) ? ds[2] : ds[0]);
            st_relaxed(act + RB_ST + ((tile * 8 + j) * 64 + 16 * wi + lr + 4 * (q & 2)) * 2 + (q & 1), nz(__float_as_uint(kk)));
            if (lane < 8) st_relaxed(g_flag + (8 * r + lane) * 192 + 128 + 32 * w + 4 * j + wi, epoch + 1);
        }
        PROFC(15);
        uint32_t h2a[32], h2b[24];
        {
            const int fa = pass_f(fs, 0), fb = pass_f(fs, 1), fc = pass_f(fs, 2);
            uint32_t* h2g = act + RB_H2 + (8 * w + 2 * wi) * 32 + lane;
            const uint32_t a0 = mkdesc(sb + OFF_Y + w * HALF, DT);
            {
                LnRow ca, cb;
                {
                    const uint32_t* sg = act + RB_ST + ((tile * 8 + 2 * q) * 64 + 16 * wi + lr) * 2;
                    uint2 u[4];
                    WAIT(B_FULLV + w, 1);
                    PROFC(16);
#pragma unroll
                    for (int i = 0; i < 4; i++) { const float2 v = lds2f(sb + OFF_X + X_STAT + w * 49152 + ((2 * q + (i >> 1)) * 64 + 16 * wi + lr + 8 * (i & 1)) * 8); u[i] = make_uint2(__float_as_uint(v.x), __float_as_uint(v.y)); }
                    while (__any_sync(~0u, min(min(min(u[0].x, u[0].y), min(u[1].x, u[1].y)), min(min(u[2].x, u[2].y), min(u[3].x, u[3].y))) == 0u)) {
#pragma unroll
                        for (int i = 0; i < 4; i++) u[i] = ld_relaxed2(sg + (i >> 1) * 128 + (i & 1) * 16);
                    }
                    warp_arrive(BAR(B_EMPTY + 3 + 3 * w));
                    float v[4] = {__uint_as_float(u[0].x) + __uint_as_float(u[2].x), __uint_as_float(u[0].y) + __uint_as_float(u[2].y),
                                  __uint_as_float(u[1].x) + __uint_as_float(u[3].x), __uint_as_float(u[1].y) + __uint_as_float(u[3].y)};
#pragma unroll
                    for (int i = 0; i < 4; i++) { v[i] += __shfl_xor_sync(~0u, v[i], 1); v[i] += __shfl_xor_sync(~0u, v[i], 2); }
                    ca = ln_coeffs(v[0] * (1.f / DM), v[1] * (1.f / DM));
                    cb = ln_coeffs(v[2] * (1.f / DM), v[3] * (1.f / DM));
                }
                const uint32_t ha = sb + OFF_Y + w * HALF + (lane >> 4) * 1024 + (2 * wi + ((lane >> 3) & 1)) * 128 + (lane & 7) * 16;
                const uint32_t sta = sb + M_ST + q * 16;
                const uint32_t* xg = act + RB_X1 + tile * 14336 + (lane >> 4) * 256 + wi * 64 + (lane & 15) * 4;
                uint32_t x[8];
                const uint32_t xs = sb + OFF_Y + w * HALF + (lane >> 4) * 1024 + wi * 256 + (lane & 15) * 16;
                uint4 st[2];
                auto load = [&](int s) {
                    if (s == 4) mbar_wait_c(BAR(B_XFULL + 4 + w), 1);
                    ldsm4(ha + s * 4096, x); ldsm4(ha + s * 4096 + 2048, x + 4);
                    st[0] = lds4(sta + s * 128); st[1] = lds4(sta + s * 128 + 64);
                };
                auto prep = [&](int s, uint32_t* f) {
                    if (__any_sync(~0u, min(min(min(x[0], x[1]), min(x[2], x[3])), min(min(x[4], x[5]), min(x[6], x[7]))) == 0u)) {
                        WG_WAIT(0);
                        x1_fix(xg, xs, s);
                        ldsm4(ha + s * 4096, x); ldsm4(ha + s * 4096 + 2048, x + 4);
                    }
#pragma unroll
                    for (int i = 0; i < 2; i++) {
                        f[4 * i] = ln_mod(ln_norm(x[4 * i], ca), st[i].x, st[i].y); f[4 * i + 1] = ln_mod(ln_norm(x[4 * i + 1], cb), st[i].x, st[i].y);
                        f[4 * i + 2] = ln_mod(ln_norm(x[4 * i + 2], ca), st[i].z, st[i].w); f[4 * i + 3] = ln_mod(ln_norm(x[4 * i + 3], cb), st[i].z, st[i].w);
                    }
                    if (s < 13) load(s + 1);
                    stsm4(ha + s * 4096, f[0], f[1], f[2], f[3]); stsm4(ha + s * 4096 + 2048, f[4], f[5], f[6], f[7]);
                };
                float ac[128];
                uint32_t fr[3][8];
                uint64_t bd = (DB128 & ~0xFFFFFFFFull) | mkdesc(sb, DB128);
                reg_def<128>(ac);
                WAIT(B_GFULL + 2 + w, 0);
                load(0);
                prep(0, fr[0]);
                PROFC(17);
#pragma unroll
                for (int s = 0; s < 14; s++) {
                    const uint32_t* f = fr[s % 3];
                    WAIT(B_FULL + g1_slot(s), s >= 7);
                    WG_FENCE();
                    wgmma_rl_256(ac, f[0], f[1], f[2], f[3], bd, s != 0);
                    wgmma_rl_256(ac, f[4], f[5], f[6], f[7], bd + 128, 1);
                    bd += s == 6 ? p.zero - 6 * 1024ull : 1024;
                    WG_COMMIT();
                    if (s < 13) prep(s + 1, fr[(s + 1) % 3]);
                    if (s > 0) { WG_WAIT(1); warp_arrive(BAR(B_EMPTY + g1_slot(s - 1))); }
                }
                fence_async_smem();
                PROFC(18);
                WG_WAIT(0);
                reg_fence<128>(ac);
                warp_arrive(BAR(B_EMPTY + 6));
#pragma unroll
                for (int g = 0; g < 16; g++) {
                    h2a[2 * g] = hmul2(pack2_relu(ac[4 * g], ac[4 * g + 1]), pack2(ac[64 + 4 * g], ac[64 + 4 * g + 1]));
                    h2a[2 * g + 1] = hmul2(pack2_relu(ac[4 * g + 2], ac[4 * g + 3]), pack2(ac[64 + 4 * g + 2], ac[64 + 4 * g + 3]));
                }
                bar_sync(1 + w, 128);
            }
            PROFC(19);
            {
                float ac[64];
                reg_def<64>(ac);
                const uint32_t bx = mkdesc(sb, dconst(8192, 1024, 1));
#pragma unroll 1
                for (int s = 0; s < 7; s++) {
                    WAIT(B_FULL + s, 0);
                    const uint32_t ad = a0 + s * 512, bd = bx + (slot_off(s) >> 4);
                    WG_FENCE();
#pragma unroll
                    for (int k = 0; k < 4; k++) wgmma_ss_128<DT, DB128>(ac, ad + k * 128, bd + k * 128, (s | k) != 0);
                    WG_COMMIT();
                    if (s == 1) {
#pragma unroll
                        for (int g = 0; g < 16; g++) { h2g[(fa / 8 + g) * 512] = h2a[2 * g]; h2g[(fa / 8 + g) * 512 + 32] = h2a[2 * g + 1]; }
                        warp_arrive(BAR(B_PUB + 6));
                    }
                    if (s > 0) { WG_WAIT(1); warp_arrive(BAR(B_EMPTY + s - 1)); }
                }
                WG_WAIT(0);
                reg_fence<64>(ac);
                warp_arrive(BAR(B_EMPTY + 6));
#pragma unroll
                for (int g = 0; g < 8; g++) {
                    h2b[2 * g] = hmul2(pack2_relu(ac[4 * g], ac[4 * g + 1]), pack2(ac[32 + 4 * g], ac[32 + 4 * g + 1]));
                    h2b[2 * g + 1] = hmul2(pack2_relu(ac[4 * g + 2], ac[4 * g + 3]), pack2(ac[32 + 4 * g + 2], ac[32 + 4 * g + 3]));
                }
            }
            PROFC(27);
            {
                float ac[32];
                reg_def<32>(ac);
                const uint32_t bx = mkdesc(sb, dconst(4096, 512, 2));
#pragma unroll 1
                for (int s = 0; s < 7; s++) {
                    WAIT(B_FULL + (s >> 1), 1);
                    const uint32_t ad = a0 + s * 512, bd = bx + s * 512;
                    WG_FENCE();
#pragma unroll
                    for (int k = 0; k < 4; k++) wgmma_ss_64<DT, dconst(4096, 512, 2)>(ac, ad + k * 128, bd + k * 64, (s | k) != 0);
                    WG_COMMIT();
                    if (s == 1) {
#pragma unroll
                        for (int g = 0; g < 8; g++) { h2g[(fb / 8 + g) * 512] = h2b[2 * g]; h2g[(fb / 8 + g) * 512 + 32] = h2b[2 * g + 1]; }
                        warp_arrive(BAR(B_PUB + 7));
                    }
                    if (s > 0 && !(s & 1)) {
                        WG_WAIT(1);
                        __syncwarp();
                        if (lane < 3) mbar_arrive(BAR(B_EMPTY + (s >> 1) - 1 + (lane ? 4 + 3 * lane : 0)));
                    }
                }
                WG_WAIT(0);
                reg_fence<32>(ac);
                PROFC(20);
#pragma unroll
                for (int g = 0; g < 4; g++) {
                    h2b[16 + 2 * g] = hmul2(pack2_relu(ac[4 * g], ac[4 * g + 1]), pack2(ac[16 + 4 * g], ac[16 + 4 * g + 1]));
                    h2b[16 + 2 * g + 1] = hmul2(pack2_relu(ac[4 * g + 2], ac[4 * g + 3]), pack2(ac[16 + 4 * g + 2], ac[16 + 4 * g + 3]));
                    h2g[(fc / 8 + g) * 512] = h2b[16 + 2 * g]; h2g[(fc / 8 + g) * 512 + 32] = h2b[16 + 2 * g + 1];
                }
                warp_arrive(BAR(B_PUB + 8));
                asm volatile("barrier.cluster.wait.aligned;" ::: "memory");
                if (lane == 0) {
                    uint32_t rb;
                    asm volatile("mapa.shared::cluster.u32 %0, %1, %2;" : "=r"(rb) : "r"(BAR(B_PEER)), "r"(kh ^ 1));
                    asm volatile("mbarrier.arrive.relaxed.cluster.shared::cluster.b64 _, [%0];" ::"r"(rb) : "memory");
                }
            }
        }
        PROFC(21);
        {
            float ac[56];
            reg_def<56>(ac);
            constexpr uint64_t DAN = dconst(2048, 128, 0);
            constexpr uint64_t DW = dconst(128, 512, 0);
            const uint32_t bx = mkdesc(sb, DW);
#pragma unroll
            for (int e = 3; e < 7; e++) {
                if (e > 3) WAIT(B_FULL + e, 1);
                const uint64_t bd = ((DW & ~0xFFFFFFFFull) | bx) + (slot_off(e) >> 4);
                const uint32_t* hh = e == 3 ? h2b + 8 : e < 6 ? h2a + 16 * (e - 4) : h2b;
                WG_FENCE();
#pragma unroll
                for (int k = e == 3 ? 2 : 0; k < 4; k++) wgmma_rl_112(ac, hh[4 * k], hh[4 * k + 1], hh[4 * k + 2], hh[4 * k + 3], bd + (k >> 1) * 512 + (k & 1) * 16, e > 3 || k > 2);
                WG_COMMIT();
                if (e > 3) { WG_WAIT(1); warp_arrive(BAR(B_EMPTY + e - 1)); }
            }
            PROFC(22);
            const uint32_t ax = mkdesc(sb + 8192 + w * 1024, DAN);
            uint32_t eb_ = BAR(B_EMPTY + 6);
            uint64_t ord = RING_ORDER;
#pragma unroll 1
            for (int e = 0; e < 21; e++) {
                const uint32_t sl = ord & 15, so = slot_off(sl) >> 4;
                ord = e == 12 ? RING_ORDER : ord >> 4;
                mbar_wait_c(BAR(B_FULL + sl), e >= 13);
                WG_FENCE();
                wgmma_ss_112<DAN, DW>(ac, ax + so, bx + so, 1);
                wgmma_ss_112<DAN, DW>(ac, ax + so + 256, bx + so + 16, 1);
                WG_COMMIT();
                WG_WAIT(1);
                warp_arrive(eb_);
                eb_ = BAR(B_EMPTY + sl);
            }
            mbar_wait_cluster(BAR(B_PEER), 0);
            WG_WAIT(0);
            reg_fence<56>(ac);
            PROFC(24);
            uint32_t rdst, rbar;
            asm volatile("mapa.shared::cluster.u32 %0, %1, %2;" : "=r"(rdst) : "r"(sb + OFF_Y + Y_XCH + w * HALF + t * 16), "r"(kh ^ 1));
            asm volatile("mapa.shared::cluster.u32 %0, %1, %2;" : "=r"(rbar) : "r"(BAR(B_XCH + w)), "r"(kh ^ 1));
#pragma unroll
            for (int g = 0; g < 3; g++)
                asm volatile("st.async.shared::cluster.mbarrier::complete_tx::bytes.v4.b32 [%0], {%1,%2,%3,%4}, [%5];" ::"r"(rdst + g * 2048),
                             "r"(pack2(ac[28 + 8 * g], ac[29 + 8 * g])), "r"(pack2(ac[30 + 8 * g], ac[31 + 8 * g])), "r"(pack2(ac[32 + 8 * g], ac[33 + 8 * g])),
                             "r"(pack2(ac[34 + 8 * g], ac[35 + 8 * g])), "r"(rbar) : "memory");
            asm volatile("st.async.shared::cluster.mbarrier::complete_tx::bytes.v2.b32 [%0], {%1,%2}, [%3];" ::"r"(rdst + 6144 - t * 8),
                         "r"(pack2(ac[52], ac[53])), "r"(pack2(ac[54], ac[55])), "r"(rbar) : "memory");
            mbar_wait_cluster(BAR(B_XCH + w), 0);
            PROFC(25);
            uint32_t op[14], rv[14];
#pragma unroll
            for (int g = 0; g < 3; g++) *(uint4*)(rv + 4 * g) = *(const uint4*)(smem + OFF_Y + Y_XCH + w * HALF + t * 16 + g * 2048);
            *(uint2*)(rv + 12) = *(const uint2*)(smem + OFF_Y + Y_XCH + w * HALF + 6144 + t * 8);
#pragma unroll
            for (int i = 0; i < 14; i++) {
                const float2 gb = *(const float2*)(smem + M_G + 224 + (8 * (i >> 1) + 2 * q) * 4);
                op[i] = pack2(fmaf(gb.x, ac[2 * i] + bf_lo(rv[i]), bf_lo(x1p[i])), fmaf(gb.y, ac[2 * i + 1] + bf_hi(rv[i]), bf_hi(x1p[i])));
            }
            WAIT(B_EMPTY + 4, 1);
            const uint32_t oc = sb + OUT_STAGE + warp * 1792;
            const uint32_t oa = oc + (((lane >> 3) & 1) * 8 + (lane & 7)) * 112 + (lane >> 4) * 16;
            stsm4(oa, op[0], op[1], op[2], op[3]); stsm4(oa + 32, op[4], op[5], op[6], op[7]); stsm4(oa + 64, op[8], op[9], op[10], op[11]);
            asm volatile("stmatrix.sync.aligned.m8n8.x2.shared.b16 [%0], {%1,%2};" ::"r"(oa + 96), "r"(op[12]), "r"(op[13]));
            fence_async_smem();
            __syncwarp();
            asm volatile("{\n.reg .pred p;\nelect.sync _|p, 0xffffffff;\n@p cp.async.bulk.tensor.3d.global.shared::cta.bulk_group [%0, {%2, %3, %4}], [%1];\n"
                         "cp.async.bulk.commit_group;\ncp.async.bulk.wait_group.read 0;\n}" ::"l"(&p.om), "r"(oc), "r"(56 * j), "r"(128 * r + 64 * w + 16 * wi), "r"(0) : "memory");
        }
        PROFC(26);
        bar_sync(1 + w, 128);
        if (wi == 0) warp_arrive(BAR(B_DONE));
        return;
    }
    helper_late(p, r, j, warp PROF_ARGS);
}

#undef act
typedef CUresult (*EncodeFn)(CUtensorMap*, CUtensorMapDataType, cuuint32_t, void*, const cuuint64_t*, const cuuint64_t*, const cuuint32_t*,
                             const cuuint32_t*, CUtensorMapInterleave, CUtensorMapSwizzle, CUtensorMapL2promotion, CUtensorMapFloatOOBfill);

static void make_map(EncodeFn fn, CUtensorMap* m, const void* ptr, uint64_t d0, uint64_t d1, uint64_t d2, uint64_t s1, uint64_t s2,
                     uint32_t b0, uint32_t b1, uint32_t b2, CUtensorMapSwizzle sw) {
    cuuint64_t dims[3] = {d0, d1, d2}, strides[2] = {s1, s2};
    cuuint32_t box[3] = {b0, b1, b2}, es[3] = {1, 1, 1};
    CUresult rc = fn(m, CU_TENSOR_MAP_DATA_TYPE_BFLOAT16, 3, (void*)ptr, dims, strides, box, es, CU_TENSOR_MAP_INTERLEAVE_NONE, sw,
                     CU_TENSOR_MAP_L2_PROMOTION_L2_128B, CU_TENSOR_MAP_FLOAT_OOB_FILL_NONE);
    (void)rc;
}

extern "C" void kernel_launch(void* const* d_in, const int* in_sizes, int n_in, void* d_out, int out_size) {
    (void)in_sizes; (void)n_in; (void)out_size;
    static EncodeFn fn = nullptr;
    static uint32_t* act_base = nullptr;
    if (!fn) {
        cudaDriverEntryPointQueryResult st;
        cudaGetDriverEntryPoint("cuTensorMapEncodeTiled", (void**)&fn, cudaEnableDefault, &st);
        void* a = nullptr;
        cudaGetSymbolAddress(&a, g_act);
        act_base = (uint32_t*)(((uintptr_t)a + 0xFFFFF) & ~(uintptr_t)0xFFFFF);
        cudaFuncSetAttribute(fused_block_kernel, cudaFuncAttributeMaxDynamicSharedMemorySize, SMEM_BYTES);
    }
    Params p;
    p.x = (const bf16*)d_in[0];
    const bf16* wqkv = (const bf16*)d_in[1];
    p.wqkv = wqkv;
    p.wop = (const bf16*)d_in[2];
    p.wg = (const bf16*)d_in[4];
    p.wu = (const bf16*)d_in[5];
    p.wd = (const bf16*)d_in[6];
    p.c = (const bf16*)d_in[7];
    p.wmod = (const bf16*)d_in[8];
    p.out = (bf16*)d_out;
    p.zero = 0;
    p.actb = act_base;
    make_map(fn, &p.wm, p.wmod, 2688, 448, 1, 5376, 5376 * 448, 16, 224, 1, CU_TENSOR_MAP_SWIZZLE_NONE);
    make_map(fn, &p.wm2, p.wmod, 2688, 448, 1, 5376, 5376 * 448, 32, 224, 1, CU_TENSOR_MAP_SWIZZLE_NONE);
    make_map(fn, &p.om, p.out, 448, 2048, 1, 896, 896 * 2048, 56, 16, 1, CU_TENSOR_MAP_SWIZZLE_NONE);
    make_map(fn, &p.xm, p.x, 448, 2048, 1, 896, 896 * 2048, 64, 128, 1, CU_TENSOR_MAP_SWIZZLE_128B);
    make_map(fn, &p.qkv, wqkv, 1344, 448, 1, 2688, 2688 * 448, 64, 224, 1, CU_TENSOR_MAP_SWIZZLE_128B);
    make_map(fn, &p.wo, p.wop, 448, 448, 1, 896, 896 * 448, 64, 224, 1, CU_TENSOR_MAP_SWIZZLE_128B);
    make_map(fn, &p.ga, p.wg, 64, 448, 28, 3584, 128, 64, 32, 2, CU_TENSOR_MAP_SWIZZLE_128B);
    make_map(fn, &p.ua, p.wu, 64, 448, 28, 3584, 128, 64, 32, 2, CU_TENSOR_MAP_SWIZZLE_128B);
    make_map(fn, &p.gb, p.wg, 64, 448, 28, 3584, 128, 64, 64, 1, CU_TENSOR_MAP_SWIZZLE_128B);
    make_map(fn, &p.ub, p.wu, 64, 448, 28, 3584, 128, 64, 64, 1, CU_TENSOR_MAP_SWIZZLE_128B);
    make_map(fn, &p.gc, p.wg, 32, 448, 56, 3584, 64, 32, 64, 1, CU_TENSOR_MAP_SWIZZLE_64B);
    make_map(fn, &p.uc, p.wu, 32, 448, 56, 3584, 64, 32, 64, 1, CU_TENSOR_MAP_SWIZZLE_64B);
    make_map(fn, &p.dn, p.wd, 8, 1792, 56, 896, 16, 8, 32, 7, CU_TENSOR_MAP_SWIZZLE_NONE);
    fused_block_kernel<<<NCTA, 384, SMEM_BYTES>>>(p);
}
```

```cpp
#include <cuda_runtime.h>
#include <cuda_bf16.h>
#include <cuda.h>
#include <stdint.h>

typedef __nv_bfloat16 bf16;

template<uint64_t CA, uint64_t CB> __device__ __forceinline__ void wgmma_sk_160(float* d, uint32_t da, uint32_t db, int sd) {
  asm volatile("{\n.reg .pred p;\n.reg .b64 a, b;\nsetp.ne.b32 p, %82, 0;\nmov.b64 a, {%80, %83};\nmov.b64 b, {%81, %84};\n"
    "wgmma.mma_async.sync.aligned.m64n160k16.f32.bf16.bf16 {%0,%1,%2,%3,%4,%5,%6,%7,%8,%9,%10,%11,%12,%13,%14,%15,%16,%17,%18,%19,%20,%21,%22,%23,%24,%25,%26,%27,%28,%29,%30,%31,%32,%33,%34,%35,%36,%37,%38,%39,%40,%41,%42,%43,%44,%45,%46,%47,%48,%49,%50,%51,%52,%53,%54,%55,%56,%57,%58,%59,%60,%61,%62,%63,%64,%65,%66,%67,%68,%69,%70,%71,%72,%73,%74,%75,%76,%77,%78,%79}, a, b, p, 1, 1, 0, 0;\n}\n"
    : "+f"(d[0]),"+f"(d[1]),"+f"(d[2]),"+f"(d[3]),"+f"(d[4]),"+f"(d[5]),"+f"(d[6]),"+f"(d[7]),"+f"(d[8]),"+f"(d[9]),"+f"(d[10]),"+f"(d[11]),"+f"(d[12]),"+f"(d[13]),"+f"(d[14]),"+f"(d[15]),"+f"(d[16]),"+f"(d[17]),"+f"(d[18]),"+f"(d[19]),"+f"(d[20]),"+f"(d[21]),"+f"(d[22]),"+f"(d[23]),"+f"(d[24]),"+f"(d[25]),"+f"(d[26]),"+f"(d[27]),"+f"(d[28]),"+f"(d[29]),"+f"(d[30]),"+f"(d[31]),"+f"(d[32]),"+f"(d[33]),"+f"(d[34]),"+f"(d[35]),"+f"(d[36]),"+f"(d[37]),"+f"(d[38]),"+f"(d[39]),"+f"(d[40]),"+f"(d[41]),"+f"(d[42]),"+f"(d[43]),"+f"(d[44]),"+f"(d[45]),"+f"(d[46]),"+f"(d[47]),"+f"(d[48]),"+f"(d[49]),"+f"(d[50]),"+f"(d[51]),"+f"(d[52]),"+f"(d[53]),"+f"(d[54]),"+f"(d[55]),"+f"(d[56]),"+f"(d[57]),"+f"(d[58]),"+f"(d[59]),"+f"(d[60]),"+f"(d[61]),"+f"(d[62]),"+f"(d[63]),"+f"(d[64]),"+f"(d[65]),"+f"(d[66]),"+f"(d[67]),"+f"(d[68]),"+f"(d[69]),"+f"(d[70]),"+f"(d[71]),"+f"(d[72]),"+f"(d[73]),"+f"(d[74]),"+f"(d[75]),"+f"(d[76]),"+f"(d[77]),"+f"(d[78]),"+f"(d[79])
    : "r"(da), "r"(db), "r"(sd), "n"((uint32_t)(CA >> 32)), "n"((uint32_t)(CB >> 32)));
}
__device__ __forceinline__ void wgmma_rl_56(float* d, uint32_t a0, uint32_t a1, uint32_t a2, uint32_t a3, uint64_t db, int sd) {
  asm volatile("{\n.reg .pred p;\nsetp.ne.b32 p, %33, 0;\n"
    "wgmma.mma_async.sync.aligned.m64n56k16.f32.bf16.bf16 {%0,%1,%2,%3,%4,%5,%6,%7,%8,%9,%10,%11,%12,%13,%14,%15,%16,%17,%18,%19,%20,%21,%22,%23,%24,%25,%26,%27}, {%28,%29,%30,%31}, %32, p, 1, 1, 1;\n}\n"
    : "+f"(d[0]),"+f"(d[1]),"+f"(d[2]),"+f"(d[3]),"+f"(d[4]),"+f"(d[5]),"+f"(d[6]),"+f"(d[7]),"+f"(d[8]),"+f"(d[9]),"+f"(d[10]),"+f"(d[11]),"+f"(d[12]),"+f"(d[13]),"+f"(d[14]),"+f"(d[15]),"+f"(d[16]),"+f"(d[17]),"+f"(d[18]),"+f"(d[19]),"+f"(d[20]),"+f"(d[21]),"+f"(d[22]),"+f"(d[23]),"+f"(d[24]),"+f"(d[25]),"+f"(d[26]),"+f"(d[27])
    : "r"(a0), "r"(a1), "r"(a2), "r"(a3), "l"(db), "r"(sd));
}
template<uint64_t CA, uint64_t CB> __device__ __forceinline__ void wgmma_ss_56(float* d, uint32_t da, uint32_t db, int sd) {
  asm volatile("{\n.reg .pred p;\n.reg .b64 a, b;\nsetp.ne.b32 p, %30, 0;\nmov.b64 a, {%28, %31};\nmov.b64 b, {%29, %32};\n"
    "wgmma.mma_async.sync.aligned.m64n56k16.f32.bf16.bf16 {%0,%1,%2,%3,%4,%5,%6,%7,%8,%9,%10,%11,%12,%13,%14,%15,%16,%17,%18,%19,%20,%21,%22,%23,%24,%25,%26,%27}, a, b, p, 1, 1, 0, 1;\n}\n"
    : "+f"(d[0]),"+f"(d[1]),"+f"(d[2]),"+f"(d[3]),"+f"(d[4]),"+f"(d[5]),"+f"(d[6]),"+f"(d[7]),"+f"(d[8]),"+f"(d[9]),"+f"(d[10]),"+f"(d[11]),"+f"(d[12]),"+f"(d[13]),"+f"(d[14]),"+f"(d[15]),"+f"(d[16]),"+f"(d[17]),"+f"(d[18]),"+f"(d[19]),"+f"(d[20]),"+f"(d[21]),"+f"(d[22]),"+f"(d[23]),"+f"(d[24]),"+f"(d[25]),"+f"(d[26]),"+f"(d[27])
    : "r"(da), "r"(db), "r"(sd), "n"((uint32_t)(CA >> 32)), "n"((uint32_t)(CB >> 32)));
}
__device__ __forceinline__ void wgmma_rl_256(float* d, uint32_t a0, uint32_t a1, uint32_t a2, uint32_t a3, uint64_t db, int sd) {
  asm volatile("{\n.reg .pred p;\nsetp.ne.b32 p, %133, 0;\n"
    "wgmma.mma_async.sync.aligned.m64n256k16.f32.bf16.bf16 {%0,%1,%2,%3,%4,%5,%6,%7,%8,%9,%10,%11,%12,%13,%14,%15,%16,%17,%18,%19,%20,%21,%22,%23,%24,%25,%26,%27,%28,%29,%30,%31,%32,%33,%34,%35,%36,%37,%38,%39,%40,%41,%42,%43,%44,%45,%46,%47,%48,%49,%50,%51,%52,%53,%54,%55,%56,%57,%58,%59,%60,%61,%62,%63,%64,%65,%66,%67,%68,%69,%70,%71,%72,%73,%74,%75,%76,%77,%78,%79,%80,%81,%82,%83,%84,%85,%86,%87,%88,%89,%90,%91,%92,%93,%94,%95,%96,%97,%98,%99,%100,%101,%102,%103,%104,%105,%106,%107,%108,%109,%110,%111,%112,%113,%114,%115,%116,%117,%118,%119,%120,%121,%122,%123,%124,%125,%126,%127}, {%128,%129,%130,%131}, %132, p, 1, 1, 1;\n}\n"
    : "+f"(d[0]),"+f"(d[1]),"+f"(d[2]),"+f"(d[3]),"+f"(d[4]),"+f"(d[5]),"+f"(d[6]),"+f"(d[7]),"+f"(d[8]),"+f"(d[9]),"+f"(d[10]),"+f"(d[11]),"+f"(d[12]),"+f"(d[13]),"+f"(d[14]),"+f"(d[15]),"+f"(d[16]),"+f"(d[17]),"+f"(d[18]),"+f"(d[19]),"+f"(d[20]),"+f"(d[21]),"+f"(d[22]),"+f"(d[23]),"+f"(d[24]),"+f"(d[25]),"+f"(d[26]),"+f"(d[27]),"+f"(d[28]),"+f"(d[29]),"+f"(d[30]),"+f"(d[31]),"+f"(d[32]),"+f"(d[33]),"+f"(d[34]),"+f"(d[35]),"+f"(d[36]),"+f"(d[37]),"+f"(d[38]),"+f"(d[39]),"+f"(d[40]),"+f"(d[41]),"+f"(d[42]),"+f"(d[43]),"+f"(d[44]),"+f"(d[45]),"+f"(d[46]),"+f"(d[47]),"+f"(d[48]),"+f"(d[49]),"+f"(d[50]),"+f"(d[51]),"+f"(d[52]),"+f"(d[53]),"+f"(d[54]),"+f"(d[55]),"+f"(d[56]),"+f"(d[57]),"+f"(d[58]),"+f"(d[59]),"+f"(d[60]),"+f"(d[61]),"+f"(d[62]),"+f"(d[63]),"+f"(d[64]),"+f"(d[65]),"+f"(d[66]),"+f"(d[67]),"+f"(d[68]),"+f"(d[69]),"+f"(d[70]),"+f"(d[71]),"+f"(d[72]),"+f"(d[73]),"+f"(d[74]),"+f"(d[75]),"+f"(d[76]),"+f"(d[77]),"+f"(d[78]),"+f"(d[79]),"+f"(d[80]),"+f"(d[81]),"+f"(d[82]),"+f"(d[83]),"+f"(d[84]),"+f"(d[85]),"+f"(d[86]),"+f"(d[87]),"+f"(d[88]),"+f"(d[89]),"+f"(d[90]),"+f"(d[91]),"+f"(d[92]),"+f"(d[93]),"+f"(d[94]),"+f"(d[95]),"+f"(d[96]),"+f"(d[97]),"+f"(d[98]),"+f"(d[99]),"+f"(d[100]),"+f"(d[101]),"+f"(d[102]),"+f"(d[103]),"+f"(d[104]),"+f"(d[105]),"+f"(d[106]),"+f"(d[107]),"+f"(d[108]),"+f"(d[109]),"+f"(d[110]),"+f"(d[111]),"+f"(d[112]),"+f"(d[113]),"+f"(d[114]),"+f"(d[115]),"+f"(d[116]),"+f"(d[117]),"+f"(d[118]),"+f"(d[119]),"+f"(d[120]),"+f"(d[121]),"+f"(d[122]),"+f"(d[123]),"+f"(d[124]),"+f"(d[125]),"+f"(d[126]),"+f"(d[127])
    : "r"(a0), "r"(a1), "r"(a2), "r"(a3), "l"(db), "r"(sd));
}
template<uint64_t CA, uint64_t CB> __device__ __forceinline__ void wgmma_ss_128(float* d, uint32_t da, uint32_t db, int sd) {
  asm volatile("{\n.reg .pred p;\n.reg .b64 a, b;\nsetp.ne.b32 p, %66, 0;\nmov.b64 a, {%64, %67};\nmov.b64 b, {%65, %68};\n"
    "wgmma.mma_async.sync.aligned.m64n128k16.f32.bf16.bf16 {%0,%1,%2,%3,%4,%5,%6,%7,%8,%9,%10,%11,%12,%13,%14,%15,%16,%17,%18,%19,%20,%21,%22,%23,%24,%25,%26,%27,%28,%29,%30,%31,%32,%33,%34,%35,%36,%37,%38,%39,%40,%41,%42,%43,%44,%45,%46,%47,%48,%49,%50,%51,%52,%53,%54,%55,%56,%57,%58,%59,%60,%61,%62,%63}, a, b, p, 1, 1, 0, 1;\n}\n"
    : "+f"(d[0]),"+f"(d[1]),"+f"(d[2]),"+f"(d[3]),"+f"(d[4]),"+f"(d[5]),"+f"(d[6]),"+f"(d[7]),"+f"(d[8]),"+f"(d[9]),"+f"(d[10]),"+f"(d[11]),"+f"(d[12]),"+f"(d[13]),"+f"(d[14]),"+f"(d[15]),"+f"(d[16]),"+f"(d[17]),"+f"(d[18]),"+f"(d[19]),"+f"(d[20]),"+f"(d[21]),"+f"(d[22]),"+f"(d[23]),"+f"(d[24]),"+f"(d[25]),"+f"(d[26]),"+f"(d[27]),"+f"(d[28]),"+f"(d[29]),"+f"(d[30]),"+f"(d[31]),"+f"(d[32]),"+f"(d[33]),"+f"(d[34]),"+f"(d[35]),"+f"(d[36]),"+f"(d[37]),"+f"(d[38]),"+f"(d[39]),"+f"(d[40]),"+f"(d[41]),"+f"(d[42]),"+f"(d[43]),"+f"(d[44]),"+f"(d[45]),"+f"(d[46]),"+f"(d[47]),"+f"(d[48]),"+f"(d[49]),"+f"(d[50]),"+f"(d[51]),"+f"(d[52]),"+f"(d[53]),"+f"(d[54]),"+f"(d[55]),"+f"(d[56]),"+f"(d[57]),"+f"(d[58]),"+f"(d[59]),"+f"(d[60]),"+f"(d[61]),"+f"(d[62]),"+f"(d[63])
    : "r"(da), "r"(db), "r"(sd), "n"((uint32_t)(CA >> 32)), "n"((uint32_t)(CB >> 32)));
}
template<uint64_t CA, uint64_t CB> __device__ __forceinline__ void wgmma_ss_64(float* d, uint32_t da, uint32_t db, int sd) {
  asm volatile("{\n.reg .pred p;\n.reg .b64 a, b;\nsetp.ne.b32 p, %34, 0;\nmov.b64 a, {%32, %35};\nmov.b64 b, {%33, %36};\n"
    "wgmma.mma_async.sync.aligned.m64n64k16.f32.bf16.bf16 {%0,%1,%2,%3,%4,%5,%6,%7,%8,%9,%10,%11,%12,%13,%14,%15,%16,%17,%18,%19,%20,%21,%22,%23,%24,%25,%26,%27,%28,%29,%30,%31}, a, b, p, 1, 1, 0, 1;\n}\n"
    : "+f"(d[0]),"+f"(d[1]),"+f"(d[2]),"+f"(d[3]),"+f"(d[4]),"+f"(d[5]),"+f"(d[6]),"+f"(d[7]),"+f"(d[8]),"+f"(d[9]),"+f"(d[10]),"+f"(d[11]),"+f"(d[12]),"+f"(d[13]),"+f"(d[14]),"+f"(d[15]),"+f"(d[16]),"+f"(d[17]),"+f"(d[18]),"+f"(d[19]),"+f"(d[20]),"+f"(d[21]),"+f"(d[22]),"+f"(d[23]),"+f"(d[24]),"+f"(d[25]),"+f"(d[26]),"+f"(d[27]),"+f"(d[28]),"+f"(d[29]),"+f"(d[30]),"+f"(d[31])
    : "r"(da), "r"(db), "r"(sd), "n"((uint32_t)(CA >> 32)), "n"((uint32_t)(CB >> 32)));
}
template<uint64_t CA, uint64_t CB> __device__ __forceinline__ void wgmma_ss_112(float* d, uint32_t da, uint32_t db, int sd) {
  asm volatile("{\n.reg .pred p;\n.reg .b64 a, b;\nsetp.ne.b32 p, %58, 0;\nmov.b64 a, {%56, %59};\nmov.b64 b, {%57, %60};\n"
    "wgmma.mma_async.sync.aligned.m64n112k16.f32.bf16.bf16 {%0,%1,%2,%3,%4,%5,%6,%7,%8,%9,%10,%11,%12,%13,%14,%15,%16,%17,%18,%19,%20,%21,%22,%23,%24,%25,%26,%27,%28,%29,%30,%31,%32,%33,%34,%35,%36,%37,%38,%39,%40,%41,%42,%43,%44,%45,%46,%47,%48,%49,%50,%51,%52,%53,%54,%55}, a, b, p, 1, 1, 0, 1;\n}\n"
    : "+f"(d[0]),"+f"(d[1]),"+f"(d[2]),"+f"(d[3]),"+f"(d[4]),"+f"(d[5]),"+f"(d[6]),"+f"(d[7]),"+f"(d[8]),"+f"(d[9]),"+f"(d[10]),"+f"(d[11]),"+f"(d[12]),"+f"(d[13]),"+f"(d[14]),"+f"(d[15]),"+f"(d[16]),"+f"(d[17]),"+f"(d[18]),"+f"(d[19]),"+f"(d[20]),"+f"(d[21]),"+f"(d[22]),"+f"(d[23]),"+f"(d[24]),"+f"(d[25]),"+f"(d[26]),"+f"(d[27]),"+f"(d[28]),"+f"(d[29]),"+f"(d[30]),"+f"(d[31]),"+f"(d[32]),"+f"(d[33]),"+f"(d[34]),"+f"(d[35]),"+f"(d[36]),"+f"(d[37]),"+f"(d[38]),"+f"(d[39]),"+f"(d[40]),"+f"(d[41]),"+f"(d[42]),"+f"(d[43]),"+f"(d[44]),"+f"(d[45]),"+f"(d[46]),"+f"(d[47]),"+f"(d[48]),"+f"(d[49]),"+f"(d[50]),"+f"(d[51]),"+f"(d[52]),"+f"(d[53]),"+f"(d[54]),"+f"(d[55])
    : "r"(da), "r"(db), "r"(sd), "n"((uint32_t)(CA >> 32)), "n"((uint32_t)(CB >> 32)));
}
__device__ __forceinline__ void wgmma_rl_112(float* d, uint32_t a0, uint32_t a1, uint32_t a2, uint32_t a3, uint64_t db, int sd) {
  asm volatile("{\n.reg .pred p;\nsetp.ne.b32 p, %61, 0;\n"
    "wgmma.mma_async.sync.aligned.m64n112k16.f32.bf16.bf16 {%0,%1,%2,%3,%4,%5,%6,%7,%8,%9,%10,%11,%12,%13,%14,%15,%16,%17,%18,%19,%20,%21,%22,%23,%24,%25,%26,%27,%28,%29,%30,%31,%32,%33,%34,%35,%36,%37,%38,%39,%40,%41,%42,%43,%44,%45,%46,%47,%48,%49,%50,%51,%52,%53,%54,%55}, {%56,%57,%58,%59}, %60, p, 1, 1, 1;\n}\n"
    : "+f"(d[0]),"+f"(d[1]),"+f"(d[2]),"+f"(d[3]),"+f"(d[4]),"+f"(d[5]),"+f"(d[6]),"+f"(d[7]),"+f"(d[8]),"+f"(d[9]),"+f"(d[10]),"+f"(d[11]),"+f"(d[12]),"+f"(d[13]),"+f"(d[14]),"+f"(d[15]),"+f"(d[16]),"+f"(d[17]),"+f"(d[18]),"+f"(d[19]),"+f"(d[20]),"+f"(d[21]),"+f"(d[22]),"+f"(d[23]),"+f"(d[24]),"+f"(d[25]),"+f"(d[26]),"+f"(d[27]),"+f"(d[28]),"+f"(d[29]),"+f"(d[30]),"+f"(d[31]),"+f"(d[32]),"+f"(d[33]),"+f"(d[34]),"+f"(d[35]),"+f"(d[36]),"+f"(d[37]),"+f"(d[38]),"+f"(d[39]),"+f"(d[40]),"+f"(d[41]),"+f"(d[42]),"+f"(d[43]),"+f"(d[44]),"+f"(d[45]),"+f"(d[46]),"+f"(d[47]),"+f"(d[48]),"+f"(d[49]),"+f"(d[50]),"+f"(d[51]),"+f"(d[52]),"+f"(d[53]),"+f"(d[54]),"+f"(d[55])
    : "r"(a0), "r"(a1), "r"(a2), "r"(a3), "l"(db), "r"(sd));
}

constexpr int DM = 448;
constexpr int NCTA = 128;
#define WIN 5
#define NPRE 14
#define VPRE 3
constexpr int SPIN_LIMIT = 1 << 22;

constexpr uint32_t OFF_X = 0, OFF_Y = 114688, OFF_MISC = 229376, SMEM_BYTES = 232448;
constexpr uint32_t Y_VR = 0, Y_K = 28672, Y_KOWN = 57344, Y_VOWN = 71680, Y_Q = 86016;
constexpr uint32_t HALF = 57344;
constexpr uint32_t X_STAT = 49152;
constexpr uint32_t OUT_STAGE = 4 * 16384;
constexpr uint32_t M_BAR = OFF_MISC;
constexpr uint32_t M_ST = OFF_MISC + 512;
constexpr uint32_t M_G = OFF_MISC + 2304;
constexpr uint32_t M_EPOCH = OFF_MISC + 3040;
enum { B_XFULL = 0, B_FULLK = 7, B_FULLV = 8, B_FULLQ, B_KRFULL, B_VRFULL, B_WOFULL, B_XCH, B_MOD1 = 15, B_FULL = 16, B_WMFULL = 30,
       B_EMPTY = 32, B_PEER = 45, B_EPOCH,
       B_PUB = 47,
       B_XFREE = B_PUB + 4, B_GEMV,
       B_WMFREE = 56, B_HRDY, B_GFULL = B_HRDY + 3, B_DONE = 31 };

__device__ uint32_t g_ticket;
__device__ __align__(128) uint32_t g_mod[8 * 6 * DM];
__device__ __align__(128) uint32_t g_flag[144 * 192];
constexpr int RB_WORDS = 262144, RB_KV = 0, RB_O = 57344, RB_X1 = 86016, RB_H2 = 143360, RB_ST = 258048;
__device__ __align__(128) uint32_t g_act[17 * RB_WORDS];
__device__ __align__(128) uint32_t g_wd[56 * 4 * 1792];
#define PROFH(id)
#define PROFH1(id)
#define PROFC(id)

struct alignas(64) Params {
    CUtensorMap wm, wm2, om, xm, qkv, wo, ga, ua, gb, ub, gc, uc, dn;
    const bf16 *x, *c, *wqkv, *wmod, *wg, *wu, *wd, *wop;
    bf16* out;
    uint32_t* actb;
    uint32_t zero;
};

__device__ __forceinline__ void mbar_init(uint32_t bar, int cnt) { asm volatile("mbarrier.init.shared::cta.b64 [%0], %1;" ::"r"(bar), "r"(cnt) : "memory"); }
__device__ __forceinline__ void mbar_arrive(uint32_t bar) { asm volatile("mbarrier.arrive.shared::cta.b64 _, [%0];" ::"r"(bar) : "memory"); }
__device__ __forceinline__ void mbar_wait(uint32_t bar, uint32_t parity) {
    uint32_t ok; int n = 0;
    do {
        asm volatile("{\n.reg .pred p;\nmbarrier.try_wait.parity.shared::cta.b64 p, [%1], %2;\nselp.u32 %0, 1, 0, p;\n}" : "=r"(ok) : "r"(bar), "r"(parity) : "memory");
        if (++n > SPIN_LIMIT) __trap();
    } while (!ok);
}
__device__ __forceinline__ void mbar_wait_c(uint32_t bar, uint32_t parity) {
    asm volatile("{\n.reg .pred p;\nWL:\nmbarrier.try_wait.parity.shared::cta.b64 p, [%0], %1, 0x989680;\n@!p bra WL;\n}" ::"r"(bar), "r"(parity) : "memory");
}
__device__ __forceinline__ void mbar_wait_cluster(uint32_t bar, uint32_t parity) {
    asm volatile("{\n.reg .pred p;\nWL:\nmbarrier.try_wait.parity.acquire.cluster.shared::cta.b64 p, [%0], %1, 0x989680;\n@!p bra WL;\n}" ::"r"(bar), "r"(parity) : "memory");
}
__device__ __forceinline__ void warp_arrive(uint32_t bar) {
    __syncwarp();
    asm volatile("{\n.reg .pred p;\nelect.sync _|p, 0xffffffff;\n@p mbarrier.arrive.shared::cta.b64 _, [%0];\n}" ::"r"(bar) : "memory");
}
__device__ __forceinline__ int opaque(int v) { return __shfl_sync(~0u, v, 0); }
__device__ __forceinline__ int fresh_tid() { int v; asm volatile("mov.u32 %0, %%tid.x;" : "=r"(v)); return v; }
__device__ __forceinline__ void bar_sync(int id, int n) { asm volatile("bar.sync %0, %1;" ::"r"(id), "r"(n) : "memory"); }
__device__ __forceinline__ void bar_arrive(int id, int n) { asm volatile("bar.arrive %0, %1;" ::"r"(id), "r"(n) : "memory"); }
__device__ __forceinline__ void fence_async_smem() { asm volatile("fence.proxy.async.shared::cta;" ::: "memory"); }
__device__ __forceinline__ void fence_async_global() { asm volatile("fence.proxy.async.global;" ::: "memory"); }
__device__ __forceinline__ void fence_gpu() { asm volatile("fence.release.gpu;" ::: "memory"); }
__device__ __forceinline__ void expect_e(uint32_t bar, uint32_t bytes) {
    asm volatile("{\n.reg .pred p;\nelect.sync _|p, 0xffffffff;\n@p mbarrier.arrive.expect_tx.shared::cta.b64 _, [%0], %1;\n}" ::"r"(bar), "r"(bytes) : "memory");
}
__device__ __forceinline__ void tma3_e(uint32_t dst, const CUtensorMap* m, int c0, int c1, int c2, uint32_t bar) {
    asm volatile("{\n.reg .pred p;\nelect.sync _|p, 0xffffffff;\n@p cp.async.bulk.tensor.3d.shared::cluster.global.mbarrier::complete_tx::bytes [%0], [%1, {%3, %4, %5}], [%2];\n}"
                 ::"r"(dst), "l"(m), "r"(bar), "r"(c0), "r"(c1), "r"(c2) : "memory");
}
__device__ __forceinline__ void bulk_e(uint32_t dst, const void* src, uint32_t bytes, uint32_t bar) {
    asm volatile("{\n.reg .pred p;\nelect.sync _|p, 0xffffffff;\n@p cp.async.bulk.shared::cluster.global.mbarrier::complete_tx::bytes [%0], [%1], %2, [%3];\n}"
                 ::"r"(dst), "l"(src), "r"(bytes), "r"(bar) : "memory");
}
__device__ __forceinline__ void init_e(uint32_t bar, int cnt) {
    asm volatile("{\n.reg .pred p;\nelect.sync _|p, 0xffffffff;\n@p mbarrier.init.shared::cta.b64 [%0], %1;\n}" ::"r"(bar), "r"(cnt) : "memory");
}
__device__ __forceinline__ void l2_prefetch_e(const void* src, uint32_t bytes) {
    asm volatile("{\n.reg .pred p;\nelect.sync _|p, 0xffffffff;\n@p cp.async.bulk.prefetch.L2.global [%0], %1;\n}" ::"l"(src), "r"(bytes) : "memory");
}
__device__ __forceinline__ uint32_t ld_relaxed(const uint32_t* p) { uint32_t v; asm volatile("ld.relaxed.gpu.global.u32 %0, [%1];" : "=r"(v) : "l"(p) : "memory"); return v; }
__device__ __forceinline__ void st_relaxed(uint32_t* p, uint32_t v) { asm volatile("st.relaxed.gpu.global.u32 [%0], %1;" ::"l"(p), "r"(v) : "memory"); }
__device__ __forceinline__ uint4 ld_relaxed4(const uint4* p) { uint4 v; asm volatile("ld.relaxed.gpu.global.v4.u32 {%0,%1,%2,%3}, [%4];" : "=r"(v.x), "=r"(v.y), "=r"(v.z), "=r"(v.w) : "l"(p) : "memory"); return v; }
__device__ __forceinline__ uint4 lds4(uint32_t a) { uint4 v; asm volatile("ld.shared.v4.u32 {%0,%1,%2,%3}, [%4];" : "=r"(v.x), "=r"(v.y), "=r"(v.z), "=r"(v.w) : "r"(a) : "memory"); return v; }
__device__ __forceinline__ float2 lds2f(uint32_t a) { float2 v; asm volatile("ld.shared.v2.f32 {%0,%1}, [%2];" : "=f"(v.x), "=f"(v.y) : "r"(a) : "memory"); return v; }
__device__ __forceinline__ uint32_t lds1(uint32_t a) { uint32_t v; asm volatile("ld.shared.u32 %0, [%1];" : "=r"(v) : "r"(a) : "memory"); return v; }
__device__ __forceinline__ void sts4(uint32_t a, uint4 v) { asm volatile("st.shared.v4.u32 [%0], {%1,%2,%3,%4};" ::"r"(a), "r"(v.x), "r"(v.y), "r"(v.z), "r"(v.w) : "memory"); }
__device__ __forceinline__ void sts1(uint32_t a, uint32_t v) { asm volatile("st.shared.u32 [%0], %1;" ::"r"(a), "r"(v) : "memory"); }
__device__ __forceinline__ void stsm4(uint32_t a, uint32_t r0, uint32_t r1, uint32_t r2, uint32_t r3) {
    asm volatile("stmatrix.sync.aligned.m8n8.x4.shared.b16 [%0], {%1,%2,%3,%4};" ::"r"(a), "r"(r0), "r"(r1), "r"(r2), "r"(r3));
}
__device__ __forceinline__ uint32_t pack2(float lo, float hi) { uint32_t r; asm("cvt.rn.bf16x2.f32 %0, %1, %2;" : "=r"(r) : "f"(hi), "f"(lo)); return r; }
__device__ __forceinline__ uint32_t pack2_relu(float lo, float hi) { uint32_t r; asm("cvt.rn.relu.bf16x2.f32 %0, %1, %2;" : "=r"(r) : "f"(hi), "f"(lo)); return r; }
__device__ __forceinline__ uint32_t hfma2(uint32_t a, uint32_t b, uint32_t c) { uint32_t r; asm("fma.rn.bf16x2 %0, %1, %2, %3;" : "=r"(r) : "r"(a), "r"(b), "r"(c)); return r; }
__device__ __forceinline__ uint32_t hmul2(uint32_t a, uint32_t b) { uint32_t r; asm("mul.rn.bf16x2 %0, %1, %2;" : "=r"(r) : "r"(a), "r"(b)); return r; }
__device__ __forceinline__ float bf_lo(uint32_t v) { return __uint_as_float(v << 16); }
__device__ __forceinline__ float bf_hi(uint32_t v) { return __uint_as_float(v & 0xFFFF0000u); }
__device__ __forceinline__ float bf_round(float v) { return bf_lo(pack2(v, 0.f)); }
__device__ __forceinline__ float ex2(float x) { float r; asm("ex2.approx.ftz.f32 %0, %1;" : "=f"(r) : "f"(x)); return r; }
__device__ __forceinline__ void mma16816(float* d, uint32_t a0, uint32_t a1, uint32_t a2, uint32_t a3, uint32_t b0, uint32_t b1) {
    asm("mma.sync.aligned.m16n8k16.row.col.f32.bf16.bf16.f32 {%0,%1,%2,%3}, {%4,%5,%6,%7}, {%8,%9}, {%0,%1,%2,%3};"
        : "+f"(d[0]), "+f"(d[1]), "+f"(d[2]), "+f"(d[3]) : "r"(a0), "r"(a1), "r"(a2), "r"(a3), "r"(b0), "r"(b1));
}
__device__ __forceinline__ void mma1688(float* d, uint32_t a0, uint32_t a1, uint32_t b0) {
    asm("mma.sync.aligned.m16n8k8.row.col.f32.bf16.bf16.f32 {%0,%1,%2,%3}, {%4,%5}, {%6}, {%0,%1,%2,%3};"
        : "+f"(d[0]), "+f"(d[1]), "+f"(d[2]), "+f"(d[3]) : "r"(a0), "r"(a1), "r"(b0));
}
__device__ __forceinline__ void ldsm4(uint32_t a, uint32_t* r) {
    asm volatile("ldmatrix.sync.aligned.m8n8.x4.shared.b16 {%0,%1,%2,%3}, [%4];" : "=r"(r[0]), "=r"(r[1]), "=r"(r[2]), "=r"(r[3]) : "r"(a));
}
__device__ __forceinline__ void ldsm4t(uint32_t a, uint32_t* r) {
    asm volatile("ldmatrix.sync.aligned.m8n8.x4.trans.shared.b16 {%0,%1,%2,%3}, [%4];" : "=r"(r[0]), "=r"(r[1]), "=r"(r[2]), "=r"(r[3]) : "r"(a));
}
__device__ __forceinline__ uint32_t nz(uint32_t v) { uint32_t r; asm("max.u32 %0, %1, 1;" : "=r"(r) : "r"(v)); return r; }
__device__ __forceinline__ float rcp(float x) { float r; asm("rcp.approx.ftz.f32 %0, %1;" : "=f"(r) : "f"(x)); return r; }
__device__ __forceinline__ uint2 ld_relaxed2(const void* p) { uint2 v; asm volatile("ld.relaxed.gpu.global.v2.u32 {%0,%1}, [%2];" : "=r"(v.x), "=r"(v.y) : "l"(p) : "memory"); return v; }
__host__ __device__ constexpr uint64_t dconst(uint32_t lbo, uint32_t sbo, uint32_t swz) {
    return ((uint64_t)(lbo >> 4) << 16) | ((uint64_t)(sbo >> 4) << 32) | ((uint64_t)swz << 62);
}
__device__ __forceinline__ uint32_t mkdesc(uint32_t addr, uint64_t c) { return (uint32_t)c | ((addr & 0x3FFFF) >> 4); }
#define WG_FENCE() asm volatile("wgmma.fence.sync.aligned;" ::: "memory")
#define WG_COMMIT() asm volatile("wgmma.commit_group.sync.aligned;" ::: "memory")
#define WG_WAIT(n) asm volatile("wgmma.wait_group.sync.aligned %0;" ::"n"(n) : "memory")
template <int N> __device__ __forceinline__ void reg_fence(float* d) {
#pragma unroll
    for (int i = 0; i < N; i++) asm volatile("" : "+f"(d[i])::"memory");
}
template <int N> __device__ __forceinline__ void reg_def(float* d) {
#pragma unroll
    for (int i = 0; i < N; i++) asm volatile("" : "=f"(d[i]));
}
template <int N> __device__ __forceinline__ void reg_def(uint32_t* d) {
#pragma unroll
    for (int i = 0; i < N; i++) asm volatile("" : "=r"(d[i]));
}
__device__ __forceinline__ void wait_flags(const uint32_t* p, uint32_t target, uint32_t mask) {
    int n = 0;
    while (~__ballot_sync(~0u, ld_relaxed(p) == target) & mask) { if (++n > SPIN_LIMIT) __trap(); }
    asm volatile("fence.acquire.gpu;" ::: "memory");
}
__device__ __forceinline__ float silu_bf(uint32_t cbits) {
    const float c = __uint_as_float(cbits << 16);
    return bf_round(__fdividef(c, 1.f + fminf(ex2(-1.4426950408889634f * c), 1e30f)));
}
__device__ __forceinline__ void gemv_part(uint32_t wmbuf, int wp, int lane) {
    const uint32_t wa = wmbuf + wp * 512 + (8 * (lane >> 4) + (lane & 7)) * 32 + ((lane >> 3) & 1) * 16;
    float d[4] = {};
#pragma unroll
    for (int i = 0; i < 4; i++) {
        uint32_t A[4];
        const float2 v = lds2f(wmbuf + 28672 + (wp + 8 * i) * 32 + (lane & 3) * 8);
        ldsm4t(wa + (i < 3 || wp < 4 ? i : 0) * 4096, A);
        mma16816(d, A[0], A[1], A[2], A[3], __float_as_uint(v.x), __float_as_uint(v.y));
    }
    if ((lane & 3) == 0) {
        sts1(wmbuf + 29696 + (wp * 16 + (lane >> 2)) * 4, __float_as_uint(d[0]));
        sts1(wmbuf + 29696 + (wp * 16 + 8 + (lane >> 2)) * 4, __float_as_uint(d[2]));
    }
}
__device__ __forceinline__ uint32_t mod_word(float v, int col, uint32_t target) {
    v = bf_round(v);
    if ((col >= DM && col < 2 * DM) || (col >= 4 * DM && col < 5 * DM)) v += 1.f;
    return (pack2(v, 0.f) << 16) | (target & 0xFFFFu);
}
__device__ __forceinline__ const uint4* mod_src(int i, int r, int j, bool p2) {
    i = min(i, p2 ? 251 : 223);
    return (const uint4*)g_mod + (r & 7) * (6 * DM / 4) + (i < 224 ? (p2 ? 336 : 0) + i : (i < 238 ? 14 * j + i : 14 * j + i + 322));
}
__device__ __forceinline__ void mod_store(uint32_t sb, uint4 v, const uint4* src, int i) {
    const uint32_t tag = lds1(sb + M_EPOCH) + 1;
    while (__any_sync(~0u, (((v.x ^ tag) | (v.y ^ tag) | (v.z ^ tag) | (v.w ^ tag)) & 0xFFFFu) != 0u)) v = ld_relaxed4(src);
    if (i < 224) {
        const int isc = i >= 112, c4 = i - 112 * isc;
        const uint32_t a = sb + M_ST + (c4 >> 2) * 64 + (c4 & 1) * 32 + (c4 & 2) * 4 + (isc ? 0 : 4);
        sts1(a, __byte_perm(v.x, v.y, 0x7632));
        sts1(a + 16, __byte_perm(v.z, v.w, 0x7632));
    } else if (i < 252) {
        sts4(sb + M_G + (i - 224) * 16, make_uint4(v.x & 0xFFFF0000u, v.y & 0xFFFF0000u, v.z & 0xFFFF0000u, v.w & 0xFFFF0000u));
    }
}
__device__ __forceinline__ int pass_f(int fs, int ps) { return 224 * fs + ((fs & 1) ? (ps == 0 ? 96 : ps == 1 ? 32 : 0) : (ps == 0 ? 0 : ps == 1 ? 128 : 192)); }
__device__ __forceinline__ constexpr uint32_t slot_off(int l) { return l * 16384 + (l >= 10 ? 8192 : 0); }
constexpr uint64_t RING_ORDER = 0x6543C92B81A70ull;
constexpr uint32_t Y_XCH = 49152;
__device__ __forceinline__ constexpr int g1_slot(int s) { return s % 7; }
__device__ __noinline__ void x1_fix(const uint32_t* g, uint32_t sa, int s) {
#pragma unroll 1
    for (int k = 4 * s; k < 4 * s + 4;) {
        const uint4 v = ld_relaxed4((const uint4*)(g + k * 256));
        sts4(sa + k * 1024, v);
        k += 2 * __all_sync(~0u, min(min(v.x, v.y), min(v.z, v.w)) != 0u);
    }
    __syncwarp();
}
struct LnRow { uint32_t nm, hi, lo; };
__device__ __forceinline__ LnRow ln_coeffs(float mean, float msq) {
    const float var = bf_round(fmaxf(msq - mean * mean, 0.f));
    float sd;
    asm("sqrt.approx.f32 %0, %1;" : "=f"(sd) : "f"(bf_round(var + 1e-5f)));
    const float inv = rcp(bf_round(sd)), hi = bf_round(inv);
    LnRow c;
    c.nm = pack2(-bf_round(mean) * hi, -bf_round(mean) * hi);
    c.hi = pack2(hi, hi);
    c.lo = pack2(inv - hi, inv - hi);
    return c;
}
__device__ __forceinline__ uint32_t ln_norm(uint32_t x, const LnRow& c) {
    return hfma2(x, c.hi, c.nm);
}
__device__ __forceinline__ uint32_t ln_mod(uint32_t y, uint32_t sc, uint32_t sh) {
    return hfma2(y, sc, sh);
}

#define LOADW bulk_e(dst, g_wd + (size_t)((f >> 5) * 4 + nq) * 1792, 7168, bar);
template <int sec> __device__ __forceinline__ void ring_loader(const Params& p, uint32_t sb_, int r_, int j_, int lane) {
    const uint32_t sb = opaque(sb_);
    const int r = opaque(r_), j = opaque(j_), nq = j >> 1, fs = 4 * (j & 1) + nq;
    const int fa = pass_f(fs, 0), fb = pass_f(fs, 1), fc = pass_f(fs, 2);
    const uint32_t* h2src = (const uint32_t*)__shfl_sync(~0u, (unsigned long long)(p.actb + (size_t)r * RB_WORDS + RB_H2), 0);
    const CUtensorMap* gmap = (const CUtensorMap*)__shfl_sync(~0u, (unsigned long long)(&p.ga + sec), 0);
#define BAR(i) (sb + M_BAR + 8 * (i))
#define kh (j & 1)
            int sl = 0;
#pragma unroll 1
            for (int s = 0; s < 21; s++) {
                if (s == 7) { wait_flags(g_flag + (8 * r + j) * 192 + 96 + lane, lds1(sb + M_EPOCH) + 1, 0xFFFFu); fence_async_global(); }
                if (s >= 1 && s < 6) mbar_wait(BAR(B_FULL + s - 1), 0);
                mbar_wait(BAR(B_EMPTY + sl), s >= 7 && s < 14);
                expect_e(BAR(B_FULL + sl), 8192);
                tma3_e(sb + slot_off(sl) + sec * 8192, gmap + (s < 14 ? 0 : 2), 0, s < 14 ? 32 * s : 64 * sl, (s < 14 ? fa : fb) >> 6, BAR(B_FULL + sl));
                sl = sl == 6 ? 0 : sl + 1;
            }
#pragma unroll 1
            for (int s = 0; s < 7; s++) {
                const uint32_t bar = BAR(B_FULL + s);
                uint32_t dst = sb + slot_off(s) + sec * 4096;
                mbar_wait(BAR(B_EMPTY + s), 1);
                expect_e(bar, s < 3 ? 8192 : s > 3 ? 7168 : sec ? 4096 : 4096 + 7168);
                if (s < 4) tma3_e(dst, gmap + 4, 0, 128 * s, fc >> 5, bar);
                if (s < 3) tma3_e(dst + 8192, gmap + 4, 0, 128 * s + 64, fc >> 5, bar);
                else if (s > 3 || !sec) {
                    const int f = s == 3 ? fc : (s < 6 ? fa + 64 * (s - 4) : fb) + 32 * sec;
                    dst = sb + slot_off(s) + (s == 3 || sec ? 8192 : 0);
                    LOADW
                }
            }
            if (!sec) PROFH(3);
            if (sec) asm volatile("prefetch.tensormap [%0];" ::"l"(&p.om) : "memory");
            int e = 0;
#pragma unroll 1
            for (int grp = 0; grp < 9; grp++) {
                const int ps = grp >= 6 ? 2 : grp >= 3 ? 1 : 0;
                int sidx = grp - 3 * ps;
                if (sec && sidx == 0) { mbar_wait(BAR(B_HRDY + ps), 0); fence_async_global(); }
                sidx += sidx >= nq;
                int f = pass_f(4 * kh + sidx, ps);
#pragma unroll 1
                for (int k = 4 >> ps; k > 0; k--, e++, f += 32) {
                    sl = (RING_ORDER >> (4 * (e < 13 ? e : e - 13))) & 15;
                    const uint32_t dst = sb + slot_off(sl), bar = BAR(B_FULL + sl);
                    mbar_wait(BAR(B_EMPTY + sl), e >= 13);
                    if (e >= WIN) mbar_wait(BAR(B_FULL + ((RING_ORDER >> (4 * (e - WIN < 13 ? e - WIN : e - WIN - 13))) & 15)), e - WIN >= 13);
                    expect_e(bar, sec ? 8192 : 7168);
                    if (!sec) { LOADW }
                    else bulk_e(dst + 8192, h2src + f * 64, 8192, bar);
                }
            }
            if (!sec) PROFH(4);
}

#define PROF_PARAMS
#define PROF_ARGS
__device__ __noinline__ void helper_late(const Params& p, int r_, int j_, int warp_ PROF_PARAMS) {
    extern __shared__ __align__(1024) unsigned char smem[];
    const uint32_t sb = (uint32_t)__cvta_generic_to_shared(smem);
    const int r = opaque(r_), j = opaque(j_), warp = opaque(warp_), nq = j >> 1, b = 8 * r + j;
    uint32_t* const act = (uint32_t*)__shfl_sync(~0u, (unsigned long long)(p.actb + (size_t)r * RB_WORDS), 0);
    {
        const int lane = fresh_tid() & 31;
        const uint32_t target = lds1(sb + M_EPOCH) + 1;
        if (warp == 8) { expect_e(BAR(B_XCH), 7168); expect_e(BAR(B_XCH + 1), 7168); }
            if (warp == 9) {
#pragma unroll 1
                for (int kv = 0; kv < 2; kv++) {
                    mbar_wait(BAR(B_PUB + kv), 0);
                    wait_flags(g_flag + b * 192 + lane, target, (r >= 2 ? 6u : r == 1 ? 2u : 0u) << (8 * kv));
                    fence_async_global();
                    const uint32_t dst = sb + OFF_Y + (kv ? Y_VR : Y_K);
                    expect_e(BAR(B_KRFULL + kv), r >= 2 ? 28672 : r == 1 ? 14336 : 0);
                    if (r >= 2) bulk_e(dst, act - 2 * RB_WORDS + RB_KV + j * 7168 + kv * 3584, 14336, BAR(B_KRFULL + kv));
                    if (r >= 1) bulk_e(dst + 14336, act - RB_WORDS + RB_KV + j * 7168 + kv * 3584, 14336, BAR(B_KRFULL + kv));
                    if (kv == 0) { PROFH(8); }
                }
            } else if (warp == 8) {
                uint4 v[8];
                mbar_wait(BAR(B_WOFULL), 0);
#pragma unroll
                for (int k = 0; k < 8; k++) v[k] = ld_relaxed4(mod_src(lane + 32 * k, r, j, true));
#pragma unroll
                for (int k = 0; k < 8; k++) mod_store(sb, v[k], mod_src(lane + 32 * k, r, j, true), lane + 32 * k);
                warp_arrive(BAR(B_MOD1));
            } else if (warp == 11) {
                if (kh == 1 && r < 14) {
                    const uint32_t wmbuf = sb + OFF_X + HALF;
                    const int mcol = 2 * DM + 32 * (4 * r + nq);
                    mbar_wait(BAR(B_XFREE), 0);
                    tma3_e(wmbuf, &p.wm2, mcol, 0, 0, BAR(B_WMFULL));
                    tma3_e(wmbuf + 14336, &p.wm2, mcol, 224, 0, BAR(B_WMFULL));
#pragma unroll 1
                    for (int wd = lane; wd < 224; wd += 32) {
                        const uint32_t cb = __ldg((const uint32_t*)p.c + wd);
                        sts1(wmbuf + 28672 + (wd >> 3) * 32 + (wd & 3) * 8 + (wd & 4), pack2(silu_bf(cb & 0xFFFFu), silu_bf(cb >> 16)));
                    }
                    __syncwarp();
                    mbar_wait(BAR(B_WMFULL), 0);
                    const uint32_t wa = wmbuf + (8 * (lane >> 4) + (lane & 7)) * 64 + ((lane >> 3) & 1) * 16;
                    float d[2][4] = {};
#pragma unroll 4
                    for (int ks = 0; ks < 28; ks++) {
                        uint32_t A[8];
                        ldsm4t(wa + ks * 1024, A); ldsm4t(wa + ks * 1024 + 32, A + 4);
                        const float2 v = lds2f(wmbuf + 28672 + ks * 32 + (lane & 3) * 8);
                        mma16816(d[0], A[0], A[1], A[2], A[3], __float_as_uint(v.x), __float_as_uint(v.y));
                        mma16816(d[1], A[4], A[5], A[6], A[7], __float_as_uint(v.x), __float_as_uint(v.y));
                    }
                    const int q = lane & 3, col = mcol + 8 * q + (lane >> 2);
                    const uint32_t word = mod_word(q == 0 ? d[0][0] : q == 1 ? d[0][2] : q == 2 ? d[1][0] : d[1][2], col, target);
#pragma unroll
                    for (int i = 0; i < 8; i++) st_relaxed(g_mod + i * 6 * DM + col, word);
                }
                warp_arrive(BAR(B_WMFREE));
                mbar_wait(BAR(B_VRFULL), 0);
                l2_prefetch_e((const char*)p.wg + (size_t)b * 12544, 12544);
                l2_prefetch_e((const char*)p.wu + (size_t)b * 12544, 12544);
#pragma unroll 1
                for (int k = 0; k < (r < 12 ? 2 : 1); k++) {
                    const int u = 28 * kh + r + 16 * k;
                    expect_e(BAR(B_XFULL + k), 7168);
                    tma3_e(sb + OFF_Y + 102400, &p.dn, 0, 32 * u, 7 * j, BAR(B_XFULL + k));
                    tma3_e(sb + OFF_Y + 102400 + 3584, &p.dn, 0, 32 * u, 7 * (j ^ 1), BAR(B_XFULL + k));
                    mbar_wait(BAR(B_XFULL + k), 1);
                    asm volatile("{\n.reg .pred p;\nelect.sync _|p, 0xffffffff;\n@p cp.async.bulk.global.shared::cta.bulk_group [%0], [%1], 7168;\n"
                                 "cp.async.bulk.commit_group;\ncp.async.bulk.wait_group 0;\n}" ::"l"(g_wd + (size_t)(u * 4 + nq) * 1792), "r"(sb + OFF_Y + 102400) : "memory");
                    __syncwarp();
                }
                warp_arrive(BAR(B_FULLK));
                fence_gpu();
                if (lane < 16) st_relaxed(g_flag + (8 * lane + j) * 192 + 96 + r, target);
            }
        if (warp == 8 || warp == 11) {
            const int sec = warp == 11;
            if (sec) ring_loader<1>(p, sb, r, j, lane); else ring_loader<0>(p, sb, r, j, lane);
            mbar_wait(BAR(B_DONE), 0);
        } else if (warp == 9) {
#pragma unroll
            for (int ev = 0; ev < 4; ev++) { expect_e(BAR(B_GFULL + ev), ev < 2 ? HALF / 2 : 16384); expect_e(BAR(B_XFULL + 2 + ev), ev < 2 ? HALF / 2 : HALF - 16384); }
            mbar_wait(BAR(B_PUB + 2), 0);
            expect_e(BAR(B_FULLV), 4096); expect_e(BAR(B_FULLQ), 4096);
            const int par = (target - 1) & 1;
#pragma unroll 1
            for (int ev = 0; ev < 4; ev++) {
                if (ev == 1) { mbar_wait(BAR(B_FULLK), 1); mbar_wait(BAR(B_PUB + 3), 0); }
                const int tile = (ev & 1) + (ev >> 1) * par * 2;
                const uint32_t dst = sb + (ev == 0 ? OFF_X : OFF_Y + (ev & 1) * HALF), first = ev < 2 ? HALF / 2 : 16384;
                const char* src = (const char*)(act + RB_O + ((ev >> 1) * 2 + tile) * 14336);
                wait_flags(g_flag + b * 192 + (ev < 2 ? 32 : 64 + 32 * ev) + lane, target, ev < 2 ? 0xFFu << (8 * ev) : ~0u);
                fence_async_global();
                if (ev >= 2) bulk_e(sb + OFF_X + X_STAT + (ev & 1) * 49152, act + RB_ST + tile * 1024, 4096, BAR(B_FULLV + (ev & 1)));
                bulk_e(dst, src, first, BAR(B_GFULL + ev));
                bulk_e(dst + first, src + first, HALF - first, BAR(B_XFULL + 2 + ev));
                if (ev) PROFH(4 + ev);
            }
            mbar_wait(BAR(B_XFULL + 5), 1);
#pragma unroll 1
            for (int hf = 0; hf < 2; hf++) {
                const int tile = (par ^ 1) * 2 + hf;
                uint4* xz = (uint4*)(act + RB_X1 + tile * 14336 + j * 1792) + lane;
#pragma unroll
                for (int i = 0; i < 14; i++) xz[i * 32] = make_uint4(0, 0, 0, 0);
                ((uint4*)(act + RB_ST + (tile * 8 + j) * 128))[lane] = make_uint4(0, 0, 0, 0);
            }
#pragma unroll 1
            for (int ps = 0; ps < 3; ps++) {
                mbar_wait(BAR(B_PUB + 6 + ps), 0);
                if (ps == 1) {
                    fence_gpu();
                    if (lane < 8) st_relaxed(g_flag + (8 * r + lane) * 192 + 72 + j, target);
                }
                wait_flags(g_flag + b * 192 + 64 + lane, target, (0x55u << kh) << (8 * ps));
                warp_arrive(BAR(B_HRDY + ps));
                PROFH(9 + ps);
            }
        } else {
#pragma unroll 1
            for (int k = 0; k < 9; k++) {
                if (k == 4 || k == 5 || k == 7) continue;
                uint32_t* fp = k < 2 ? g_flag + (b + 8 * lane) * 192 + k * 8 + lane : g_flag + (8 * r + lane) * 192 + 16 + k * 8 + j;
                mbar_wait(BAR(B_PUB + k), 0);
                fence_gpu();
                if (k < 2 ? (lane == 1 || lane == 2) : lane < 8) st_relaxed(fp, target);
                if (k >= 3 && k <= 5) PROFH(k - 3);
            }
        }
    }
}

__global__ void __cluster_dims__(2, 1, 1) __launch_bounds__(384, 1) fused_block_kernel(const __grid_constant__ Params p) {
    extern __shared__ __align__(1024) unsigned char smem[];
    const uint32_t sb = (uint32_t)__cvta_generic_to_shared(smem);
    const int tid = threadIdx.x, lane = tid & 31, warp = __shfl_sync(~0u, tid >> 5, 0);
    const int m = blockIdx.x >> 1;
    int r, nq;
    if (m < 4) { r = 15; nq = m; }
    else if (m < 36) { r = (m - 4) & 7; nq = (m - 4) >> 3; }
    else { nq = (m - 36) / 7; r = m - 28 - 7 * nq; }
    const int j = opaque(2 * nq + (blockIdx.x & 1)), b = 8 * r + j, fs = 4 * kh + nq;
#define act (p.actb + (size_t)r * RB_WORDS)
    uint32_t ticket = 0;
    if (tid == 288) ticket = atomicAdd(&g_ticket, 1u);
    if (warp == 10 && blockIdx.x < 112) {
#pragma unroll
        for (int i = 0; i < 4; i++) l2_prefetch_e(p.wmod + (size_t)(4 * blockIdx.x + i) * (6 * DM), 4 * DM);
    }
    if (warp == 11) l2_prefetch_e((const char*)p.x + (size_t)blockIdx.x * 14336, 14336);
    if (lane == 0 && warp < 9 && warp != 6 && warp != 7) {
        const int i0 = warp == 8 ? 0 : 8 + 8 * warp, cnt = warp == 0 || warp == 8 ? 1 : warp < 3 ? 2 : 8;
#pragma unroll
        for (int k = 0; k < 8; k++) if (i0 + k != B_WMFULL) mbar_init(BAR(i0 + k), cnt);
        if (warp == 8) mbar_init(BAR(B_WMFULL), 1);
        asm volatile("fence.mbarrier_init.release.cluster;" ::: "memory");
        fence_async_smem();
    }

    if (warp >= 8) {
        const int lane = fresh_tid() & 31;
        const bool early = kh == 0, gemv = r < 14;
        const int mcol = early ? 16 * (4 * r + nq) : 2 * DM + 32 * (4 * r + nq);
        const uint32_t wmbuf = sb + OFF_Y + HALF;
        if (warp == 8) {
            __syncwarp();
            expect_e(BAR(B_WMFULL), gemv ? 28672 >> early : 0);
            if (early && gemv) { tma3_e(wmbuf, &p.wm, mcol, 0, 0, BAR(B_WMFULL)); tma3_e(wmbuf + 7168, &p.wm, mcol, 224, 0, BAR(B_WMFULL)); }
#pragma unroll
            for (int kb = 0; kb < 7; kb++) {
                expect_e(BAR(B_XFULL + kb), 16384);
                tma3_e(sb + OFF_X + kb * 16384, &p.xm, 64 * kb, 128 * r, 0, BAR(B_XFULL + kb));
            }
        }
        asm volatile("setmaxnreg.dec.sync.aligned.u32 56;");
        if (warp == 10) {
#pragma unroll
            for (int i = 56; i < 64; i++) init_e(BAR(i), 1);
            fence_async_smem();
        }
        bar_arrive(0, 384);
        asm volatile("barrier.cluster.arrive.relaxed.aligned;" ::: "memory");
        if (warp == 8) {
            mbar_wait(BAR(B_XFULL), 0);
            l2_prefetch_e((const char*)p.wqkv + (size_t)b * 9408, 9408);
#pragma unroll 1
            for (int mt = 0; mt < 4; mt++) {
                if (mt == 1) bar_sync(9, 384);
                if (mt == 3) mbar_wait(BAR(B_WMFREE), 0);
                if (mt == 1 && early) mbar_wait(BAR(B_WMFREE), 0);
                if (mt) mbar_wait(BAR(mt == 1 ? B_FULLK : mt == 2 ? B_MOD1 : B_VRFULL), 0);
                const uint32_t bar = BAR(mt == 3 ? B_WOFULL : B_FULLK + mt), dst = sb + (mt < 2 ? OFF_Y : OFF_X) + (mt & 1) * HALF;
                const int c0 = (mt < 2 ? DM + DM * mt : 0) + 56 * j - 8 * kh;
                expect_e(bar, HALF);
                tma3_e(dst, mt == 3 ? &p.wo : &p.qkv, c0, 0, 0, bar);
                tma3_e(dst + HALF / 2, mt == 3 ? &p.wo : &p.qkv, c0, 224, 0, bar);
            }
        } else {
            if (warp == 10 && lane < 13) asm volatile("prefetch.tensormap [%0];" ::"l"(&p.wm + lane) : "memory");
            if (tid == 288) sts1(sb + M_EPOCH, ticket / NCTA);
            bar_sync(9, 384);
            if (warp == 9 && lane < 8) mbar_arrive(BAR(B_EPOCH));
            if (warp == 11 && early) {
                const uint32_t target = lds1(sb + M_EPOCH) + 1;
                mbar_wait(BAR(B_GEMV), 0);
                float sum = 0.f;
#pragma unroll
                for (int i = 0; i < 8; i++) sum += *(const float*)(smem + OFF_Y + HALF + 29696 + (i * 16 + (lane & 15)) * 4);
                uint32_t* mg = g_mod + mcol + (lane & 15) + (lane >> 4) * 4 * 6 * DM;
                const uint32_t word = mod_word(sum, mcol, target);
                if (gemv) { st_relaxed(mg, word); st_relaxed(mg + 6 * DM, word); st_relaxed(mg + 12 * DM, word); st_relaxed(mg + 18 * DM, word); }
            }
        }
    }
    if (warp < 8) {
        const int w = (warp >> 2) ^ 1, wi = warp & 3;
#define COORDS const int t = fresh_tid() & 127, lane = t & 31, q = lane & 3, lr = lane >> 2, ra = 64 * w + 16 * wi + lr; \
        const uint32_t lx = (lane >> 4) ^ (lane & 7), mrow = (64 * w + 16 * wi + ((lane >> 3) & 1) * 8 + (lane & 7)) * 128; \
        (void)q; (void)lr; (void)ra; (void)lx; (void)mrow;
#define WAIT(i, par) mbar_wait_c(BAR(i), par)
        constexpr uint64_t DB128 = dconst(4096, 1024, 1);
        {
            const int wd = fresh_tid();
            const uint32_t cb = wd < 224 ? __ldg((const uint32_t*)p.c + wd) : 0u;
            sts1(sb + OFF_Y + HALF + 28672 + (wd >> 3) * 32 + (wd & 3) * 8 + (wd & 4), pack2(silu_bf(cb & 0xFFFFu), silu_bf(cb >> 16)));
        }
        bar_arrive(9, 384);
        bar_sync(0, 384);
        asm volatile("barrier.cluster.arrive.relaxed.aligned;" ::: "memory");
        asm volatile("setmaxnreg.inc.sync.aligned.u32 224;");
        PROFC(0);
        uint32_t xr[16];
        {
            COORDS
            uint32_t h[112];
            LnRow ca, cb;
            const int mi = min(128 * w + t, 223);
            const uint4* msrc = mod_src(mi, r, j, false);
            uint4 mv;
            {
                float ds[4] = {}, dq[4] = {};
                const uint32_t ONE2 = 0x3F803F80u;
#pragma unroll
                for (int kb = 0; kb < 7; kb++) {
                    if (kb == 0 && kh == 0) { WAIT(B_WMFULL, 0); gemv_part(sb + OFF_Y + HALF, warp, lane); warp_arrive(BAR(B_GEMV)); }
                    WAIT(B_XFULL + kb, 0);
#pragma unroll
                    for (int k4 = 0; k4 < 4; k4++) ldsm4(sb + OFF_X + mrow + kb * 16384 + (((2 * k4) ^ lx) << 4), h + 16 * kb + 4 * k4);
#pragma unroll
                    for (int k4 = 0; k4 < 4; k4++) {
                        const uint32_t* f = h + 16 * kb + 4 * k4;
                        mma16816(ds, f[0], f[1], f[2], f[3], ONE2, ONE2);
                        mma16816(dq, hmul2(f[0], f[0]), hmul2(f[1], f[1]), hmul2(f[2], f[2]), hmul2(f[3], f[3]), ONE2, ONE2);
                    }
                }
#pragma unroll
                for (int i = 0; i < 4; i++) {
                    const int ch = 7 * j + 2 * i + (lane >> 4);
                    ldsm4(sb + OFF_X + mrow + (ch >> 3) * 16384 + (((ch ^ lane) & 7) << 4), xr + 4 * i);
                }
                mv = ld_relaxed4(msrc);
                warp_arrive(BAR(B_XFREE));
                float qa = dq[0], qb = dq[2];
                if (__any_sync(~0u, !(ds[0] * ds[0] <= (0.8f * DM) * qa && ds[2] * ds[2] <= (0.8f * DM) * qb))) {
                    float da[4] = {}, db[4] = {};
#pragma unroll
                    for (int i = 0; i < 112; i += 2) { mma1688(da, h[i], h[i + 1], h[i]); mma1688(db, h[i], h[i + 1], h[i + 1]); }
                    const int src = (lane & ~3) | (lr >> 1);
                    qa = __shfl_sync(~0u, (lr & 1) ? da[1] : da[0], src);
                    qb = __shfl_sync(~0u, (lr & 1) ? db[3] : db[2], src);
                }
                ca = ln_coeffs(ds[0] * (1.f / DM), qa * (1.f / DM));
                cb = ln_coeffs(ds[2] * (1.f / DM), qb * (1.f / DM));
#pragma unroll
                for (int i = 0; i < 4 * NPRE; i += 2) { h[i] = ln_norm(h[i], ca); h[i + 1] = ln_norm(h[i + 1], cb); }
            }
            PROFC(1);
            {
                float ak[28], av[28], aq[28];
                uint32_t kp[14], vp[14];
                const uint64_t bq0 = (DB128 & ~0xFFFFFFFFull) | (mkdesc(sb + OFF_X, DB128) + kh), bk0 = bq0 + (OFF_Y >> 4), bv0 = bk0 + (HALF >> 4);
                uint32_t* kvg = act + RB_KV + j * 7168 + (8 * w + 2 * wi) * 224 + lane;
                WAIT(B_EPOCH, 0);
                mod_store(sb, mv, msrc, mi);
                bar_sync(3, 256);
                if (warp == 0) warp_arrive(BAR(B_MOD1));
                WAIT(B_FULLK, 0);
                PROFC(2);
                reg_def<28>(ak);
#pragma unroll
                for (int g4 = 0; g4 < 4; g4++) {
#pragma unroll
                    for (int ks = 7 * g4; ks < 7 * g4 + 7; ks++) {
                        const uint4 st = *(const uint4*)(smem + M_ST + ks * 64 + q * 16);
                        if (ks >= NPRE) {
                            h[4 * ks] = ln_norm(h[4 * ks], ca); h[4 * ks + 1] = ln_norm(h[4 * ks + 1], cb);
                            h[4 * ks + 2] = ln_norm(h[4 * ks + 2], ca); h[4 * ks + 3] = ln_norm(h[4 * ks + 3], cb);
                        }
                        h[4 * ks] = ln_mod(h[4 * ks], st.x, st.y); h[4 * ks + 1] = ln_mod(h[4 * ks + 1], st.x, st.y);
                        h[4 * ks + 2] = ln_mod(h[4 * ks + 2], st.z, st.w); h[4 * ks + 3] = ln_mod(h[4 * ks + 3], st.z, st.w);
                    }
                    WG_FENCE();
#pragma unroll
                    for (int ks = 7 * g4; ks < 7 * g4 + 7; ks++) wgmma_rl_56(ak, h[4 * ks], h[4 * ks + 1], h[4 * ks + 2], h[4 * ks + 3], bk0 + ks * 128, ks != 0);
                }
                WG_COMMIT();
                PROFC(3);
                reg_def<28>(av);
                WG_WAIT(0);
                reg_fence<28>(ak);
#pragma unroll
                for (int g = 0; g < 7; g++) {
                    kp[2 * g] = pack2(ak[4 * g], ak[4 * g + 1]); kp[2 * g + 1] = pack2(ak[4 * g + 2], ak[4 * g + 3]);
                    kvg[g * 32] = kp[2 * g]; kvg[224 + g * 32] = kp[2 * g + 1];
                }
                warp_arrive(BAR(B_PUB));
                PROFC(4);
                WAIT(B_FULLV, 0);
                WG_FENCE();
#pragma unroll
                for (int ks = 0; ks < 28; ks++) wgmma_rl_56(av, h[4 * ks], h[4 * ks + 1], h[4 * ks + 2], h[4 * ks + 3], bv0 + ks * 128, ks != 0);
                WG_COMMIT();
                reg_def<28>(aq);
                WAIT(B_FULLQ, 0);
                WG_FENCE();
#pragma unroll
                for (int ks = 0; ks < VPRE; ks++) wgmma_rl_56(aq, h[4 * ks], h[4 * ks + 1], h[4 * ks + 2], h[4 * ks + 3], bq0 + ks * 128, ks != 0);
                WG_COMMIT();
                WG_WAIT(1);
                reg_fence<28>(av);
#pragma unroll
                for (int g = 0; g < 7; g++) {
                    vp[2 * g] = pack2(av[4 * g], av[4 * g + 1]); vp[2 * g + 1] = pack2(av[4 * g + 2], av[4 * g + 3]);
                    kvg[3584 + g * 32] = vp[2 * g]; kvg[3584 + 224 + g * 32] = vp[2 * g + 1];
                }
                warp_arrive(BAR(B_PUB + 1));
                PROFC(5);
                WG_FENCE();
#pragma unroll
                for (int ks = VPRE; ks < 28; ks++) wgmma_rl_56(aq, h[4 * ks], h[4 * ks + 1], h[4 * ks + 2], h[4 * ks + 3], bq0 + ks * 128, ks != 0);
                WG_COMMIT();
                WAIT(B_PUB + 1, 0);
                const uint32_t rg = 8 * w + 2 * wi + ((lane >> 3) & 1);
                const uint32_t ko = sb + OFF_Y + Y_KOWN + rg * 896 + (lane & 7) * 16, qo = sb + OFF_Y + Y_Q + rg * 1024 + (lane >> 4) * 128 + (lane & 7) * 16;
#pragma unroll
                for (int g = 0; g < 6; g += 2) {
                    stsm4(ko + (g + (lane >> 4)) * 128, kp[2 * g], kp[2 * g + 1], kp[2 * g + 2], kp[2 * g + 3]);
                    stsm4(ko + (Y_VOWN - Y_KOWN) + (g + (lane >> 4)) * 128, vp[2 * g], vp[2 * g + 1], vp[2 * g + 2], vp[2 * g + 3]);
                }
                stsm4(ko + (lane >> 4) * (Y_VOWN - Y_KOWN) + 6 * 128, kp[12], kp[13], vp[12], vp[13]);
                WG_WAIT(0);
                reg_fence<28>(aq);
                __syncwarp();
                if (lane < 3 && w == 1) mbar_arrive(BAR(B_EMPTY + lane));
                uint32_t qp[14];
#pragma unroll
                for (int i = 0; i < 14; i++) qp[i] = pack2(aq[2 * i], aq[2 * i + 1]);
                stsm4(qo, qp[0], qp[1], qp[2], qp[3]);
                stsm4(qo + 256, qp[4], qp[5], q < 2 ? qp[6] : 0u, q < 2 ? qp[7] : 0u);
                stsm4(qo + 512, q < 2 ? 0u : qp[6], q < 2 ? 0u : qp[7], qp[8], qp[9]);
                stsm4(qo + 768, qp[10], qp[11], qp[12], qp[13]);
                fence_async_smem();
                if (w == 0) { bar_arrive(4, 256); bar_sync(1, 128); } else { bar_arrive(5, 256); bar_sync(4, 256); }
            }
        }
        PROFC(6);
        WAIT(B_KRFULL, 0);
        PROFC(7);
        {
#pragma unroll 1
            for (int hf = 0; hf < 2; hf++) {
                COORDS
                if (hf > w) bar_sync(5, 256);
                float s[160];
                const float CS = 0.18898223650461361f * 1.4426950408889634f;
                const float NEG = __int_as_float(0xFF800000);
                constexpr uint64_t DQ = dconst(128, 1024, 0), DK = dconst(128, 896, 0);
                {
                    const uint32_t qd = mkdesc(sb + OFF_Y + Y_Q + hf * 8192 + w * 512, DQ), kd = mkdesc(sb + OFF_Y + Y_K + hf * 8 * 896 + w * 384, DK);
                    reg_def<160>(s);
                    WG_FENCE();
                    wgmma_sk_160<DQ, DK>(s, qd, kd, 0);
                    wgmma_sk_160<DQ, DK>(s, qd + 16, kd + 16, 1);
                    wgmma_sk_160<DQ, DK>(s + 80, qd, kd + 20 * 56, 0);
                    wgmma_sk_160<DQ, DK>(s + 80, qd + 16, kd + 20 * 56 + 16, 1);
                    WG_COMMIT();
                    WG_WAIT(0);
                    reg_fence<160>(s);
                }
                if (r < 2) {
                    const int pmin = 4 - 2 * r - hf;
#pragma unroll
                    for (int p4 = 0; p4 < 4; p4++)
                        if (p4 < pmin) {
#pragma unroll
                            for (int i = 0; i < 32; i++) asm volatile("mov.b32 %0, 0xFF800000;" : "=f"(s[32 * p4 + i]));
                        }
                }
                const bool c0 = 2 * q > lr, c1 = 2 * q + 1 > lr;
#pragma unroll
                for (int pp = 0; pp < 4; pp++) {
                    const bool me = pp == wi;
                    float* e = s + 8 * pp;
                    if (me && !c0) { e[0] = NEG; e[6] = NEG; }
                    if (me && !c1) { e[1] = NEG; e[7] = NEG; }
                    if (me) { e[2] = NEG; e[3] = NEG; }
                    e = s + 8 * (pp + 16);
                    if (me && c0) { e[0] = NEG; e[6] = NEG; }
                    if (me && c1) { e[1] = NEG; e[7] = NEG; }
                    if (me) { e[4] = NEG; e[5] = NEG; }
                }
#pragma unroll
                for (int i = 0; i < 24; i++) s[i] = (i >> 3) < wi ? s[136 + i] : s[i];
                int i0 = 0x80000000, i1 = 0x80000000, i2 = 0x80000000, i3 = 0x80000000;
#pragma unroll
                for (int pp = 0; pp < 17; pp++) {
                    const float* e = s + 8 * pp;
                    i0 = __vimax3_s32(i0, __float_as_int(e[0]), __float_as_int(e[1])); i1 = __vimax3_s32(i1, __float_as_int(e[2]), __float_as_int(e[3]));
                    i2 = __vimax3_s32(i2, __float_as_int(e[4]), __float_as_int(e[5])); i3 = __vimax3_s32(i3, __float_as_int(e[6]), __float_as_int(e[7]));
                }
                i0 = max(i0, i2); i1 = max(i1, i3);
                i0 = max(i0, __shfl_xor_sync(~0u, i0, 1)); i1 = max(i1, __shfl_xor_sync(~0u, i1, 1));
                i0 = max(i0, __shfl_xor_sync(~0u, i0, 2)); i1 = max(i1, __shfl_xor_sync(~0u, i1, 2));
                if (__any_sync(~0u, (i0 | i1) < 0)) {
                    uint32_t u0 = ~0u, u1 = ~0u, u2 = ~0u, u3 = ~0u;
#pragma unroll
                    for (int pp = 0; pp < 17; pp++) {
                        const float* e = s + 8 * pp;
                        u0 = __vimin3_u32(u0, __float_as_uint(e[0]), __float_as_uint(e[1])); u1 = __vimin3_u32(u1, __float_as_uint(e[2]), __float_as_uint(e[3]));
                        u2 = __vimin3_u32(u2, __float_as_uint(e[4]), __float_as_uint(e[5])); u3 = __vimin3_u32(u3, __float_as_uint(e[6]), __float_as_uint(e[7]));
                    }
                    u0 = min(u0, u2); u1 = min(u1, u3);
                    u0 = min(u0, __shfl_xor_sync(~0u, u0, 1)); u1 = min(u1, __shfl_xor_sync(~0u, u1, 1));
                    u0 = min(u0, __shfl_xor_sync(~0u, u0, 2)); u1 = min(u1, __shfl_xor_sync(~0u, u1, 2));
                    if (i0 < 0) i0 = u0;
                    if (i1 < 0) i1 = u1;
                }
                const float ma = __int_as_float(i0), mb = __int_as_float(i1);
                const float na = -ma * CS, nb = -mb * CS;
                PROFC(8 + 3 * hf);
                {
                    WAIT(B_VRFULL, 0);
                    float o[16] = {}, rs[4] = {};
                    const uint32_t va = sb + OFF_Y + Y_VR + (8 * hf + ((lane >> 3) & 1)) * 896 + (3 * w + (lane >> 4)) * 128 + (lane & 7) * 16;
                    constexpr uint32_t OWN = Y_VOWN - 32 * 896;
#pragma unroll
                    for (int pp = 0; pp < 17; pp++) {
                        uint32_t B[8];
                        const uint32_t v = va + pp * 1792 + (pp < 3 ? (pp < wi ? 17 * 1792 + OWN : 0) : pp == 16 ? OWN : pp >= 12 ? hf * OWN : 0);
                        ldsm4t(v, B); ldsm4t(v + 256, B + 4);
                        float e[8];
#pragma unroll
                        for (int i = 0; i < 8; i++) e[i] = ex2(fmaf(s[8 * pp + i], CS, (i & 2) ? nb : na));
                        const uint32_t p0 = pack2(e[0], e[1]), p1 = pack2(e[2], e[3]), p2 = pack2(e[4], e[5]), p3 = pack2(e[6], e[7]);
                        mma16816(rs, p0, p1, p2, p3, 0x3F803F80u, 0x3F803F80u);
#pragma unroll
                        for (int g = 0; g < 4; g++) mma16816(o + 4 * g, p0, p1, p2, p3, B[2 * g], B[2 * g + 1]);
                    }
                    PROFC(9 + 3 * hf);
                    const float ia = rcp(rs[0]), ib = rcp(rs[2]);
                    uint32_t* og = act + RB_O + hf * 14336 + (7 * j + 3 * w) * 256 + wi * 64 + lane;
#pragma unroll
                    for (int g = 0; g < 4; g++) {
                        if ((g == 3 - 3 * w) ? ((q >> 1) == w) : true) {
                            og[g * 256] = pack2(o[4 * g] * ia, o[4 * g + 1] * ia);
                            og[g * 256 + 32] = pack2(o[4 * g + 2] * ib, o[4 * g + 3] * ib);
                        }
                    }
                    warp_arrive(BAR(B_PUB + 2 + hf));
                    PROFC(10 + 3 * hf);
                }
            }
        }
        uint32_t x1p[14];
        COORDS
        constexpr uint64_t DT = dconst(1024, 128, 0);
        const uint32_t epoch = lds1(sb + M_EPOCH);
        const int tile = opaque((epoch & 1) * 2 + w);
        {
            float ac[28];
            const uint32_t ad = mkdesc(sb + (w ? OFF_Y + HALF : OFF_X), DT), bd = mkdesc(sb + OFF_X + HALF, DB128) + kh;
            WAIT(B_WOFULL, 0);
            WAIT(B_MOD1, 1);
            WAIT(B_GFULL + w, 0);
            PROFC(28);
            reg_def<28>(ac);
#pragma unroll 1
            for (int u = 0; u < 4; u++) {
                if (u == 2) WAIT(B_XFULL + 2 + w, 1);
                WG_FENCE();
#pragma unroll
                for (int i = 0; i < 7; i++) wgmma_ss_56<DT, DB128>(ac, ad + (7 * u + i) * 128, bd + (7 * u + i) * 128, (u | i) != 0);
            }
            WG_COMMIT();
            WG_WAIT(0);
            reg_fence<28>(ac);
            PROFC(14);
            __syncwarp();
            if (lane < 3) mbar_arrive(BAR(B_EMPTY + 4 - w + lane));
            if (lane < 3 && w == 0) mbar_arrive(BAR(B_EMPTY + lane));
            float ds[4] = {}, da[4] = {}, db[4] = {};
            uint32_t* xo = act + RB_X1 + tile * 14336 + 7 * j * 256 + wi * 64 + lane;
#pragma unroll
            for (int g = 0; g < 7; g++) {
                const float2 ga = *(const float2*)(smem + M_G + (8 * g + 2 * q) * 4);
                x1p[2 * g] = pack2(fmaf(ga.x, ac[4 * g], bf_lo(xr[2 * g])), fmaf(ga.y, ac[4 * g + 1], bf_hi(xr[2 * g])));
                x1p[2 * g + 1] = pack2(fmaf(ga.x, ac[4 * g + 2], bf_lo(xr[2 * g + 1])), fmaf(ga.y, ac[4 * g + 3], bf_hi(xr[2 * g + 1])));
                st_relaxed(xo + g * 256, nz(x1p[2 * g])); st_relaxed(xo + g * 256 + 32, nz(x1p[2 * g + 1]));
                mma1688(ds, x1p[2 * g], x1p[2 * g + 1], 0x3F803F80u);
                mma1688(da, x1p[2 * g], x1p[2 * g + 1], x1p[2 * g]);
                mma1688(db, x1p[2 * g], x1p[2 * g + 1], x1p[2 * g + 1]);
            }
            const int src = (lane & ~3) | (lr >> 1);
            const float qa = __shfl_sync(~0u, (lr & 1) ? da[1] : da[0], src), qb = __shfl_sync(~0u, (lr & 1) ? db[3] : db[2], src);
            const float kk = (q & 1) ? ((q & 2) ? qb : qa) : ((q & 2) ? ds[2] : ds[0]);
            st_relaxed(act + RB_ST + ((tile * 8 + j) * 64 + 16 * wi + lr + 4 * (q & 2)) * 2 + (q & 1), nz(__float_as_uint(kk)));
            if (lane < 8) st_relaxed(g_flag + (8 * r + lane) * 192 + 128 + 32 * w + 4 * j + wi, epoch + 1);
        }
        PROFC(15);
        uint32_t h2a[32], h2b[24];
        {
            const int fa = pass_f(fs, 0), fb = pass_f(fs, 1), fc = pass_f(fs, 2);
            uint32_t* h2g = act + RB_H2 + (8 * w + 2 * wi) * 32 + lane;
            const uint32_t a0 = mkdesc(sb + OFF_Y + w * HALF, DT);
            {
                LnRow ca, cb;
                {
                    const uint32_t* sg = act + RB_ST + ((tile * 8 + 2 * q) * 64 + 16 * wi + lr) * 2;
                    uint2 u[4];
                    WAIT(B_FULLV + w, 1);
                    PROFC(16);
#pragma unroll
                    for (int i = 0; i < 4; i++) { const float2 v = lds2f(sb + OFF_X + X_STAT + w * 49152 + ((2 * q + (i >> 1)) * 64 + 16 * wi + lr + 8 * (i & 1)) * 8); u[i] = make_uint2(__float_as_uint(v.x), __float_as_uint(v.y)); }
                    while (__any_sync(~0u, min(min(min(u[0].x, u[0].y), min(u[1].x, u[1].y)), min(min(u[2].x, u[2].y), min(u[3].x, u[3].y))) == 0u)) {
#pragma unroll
                        for (int i = 0; i < 4; i++) u[i] = ld_relaxed2(sg + (i >> 1) * 128 + (i & 1) * 16);
                    }
                    warp_arrive(BAR(B_EMPTY + 3 + 3 * w));
                    float v[4] = {__uint_as_float(u[0].x) + __uint_as_float(u[2].x), __uint_as_float(u[0].y) + __uint_as_float(u[2].y),
                                  __uint_as_float(u[1].x) + __uint_as_float(u[3].x), __uint_as_float(u[1].y) + __uint_as_float(u[3].y)};
#pragma unroll
                    for (int i = 0; i < 4; i++) { v[i] += __shfl_xor_sync(~0u, v[i], 1); v[i] += __shfl_xor_sync(~0u, v[i], 2); }
                    ca = ln_coeffs(v[0] * (1.f / DM), v[1] * (1.f / DM));
                    cb = ln_coeffs(v[2] * (1.f / DM), v[3] * (1.f / DM));
                }
                const uint32_t ha = sb + OFF_Y + w * HALF + (lane >> 4) * 1024 + (2 * wi + ((lane >> 3) & 1)) * 128 + (lane & 7) * 16;
                const uint32_t sta = sb + M_ST + q * 16;
                const uint32_t* xg = act + RB_X1 + tile * 14336 + (lane >> 4) * 256 + wi * 64 + (lane & 15) * 4;
                uint32_t x[8];
                const uint32_t xs = sb + OFF_Y + w * HALF + (lane >> 4) * 1024 + wi * 256 + (lane & 15) * 16;
                uint4 st[2];
                auto load = [&](int s) {
                    if (s == 4) mbar_wait_c(BAR(B_XFULL + 4 + w), 1);
                    ldsm4(ha + s * 4096, x); ldsm4(ha + s * 4096 + 2048, x + 4);
                    st[0] = lds4(sta + s * 128); st[1] = lds4(sta + s * 128 + 64);
                };
                auto prep = [&](int s, uint32_t* f) {
                    if (__any_sync(~0u, min(min(min(x[0], x[1]), min(x[2], x[3])), min(min(x[4], x[5]), min(x[6], x[7]))) == 0u)) {
                        WG_WAIT(0);
                        x1_fix(xg, xs, s);
                        ldsm4(ha + s * 4096, x); ldsm4(ha + s * 4096 + 2048, x + 4);
                    }
#pragma unroll
                    for (int i = 0; i < 2; i++) {
                        f[4 * i] = ln_mod(ln_norm(x[4 * i], ca), st[i].x, st[i].y); f[4 * i + 1] = ln_mod(ln_norm(x[4 * i + 1], cb), st[i].x, st[i].y);
                        f[4 * i + 2] = ln_mod(ln_norm(x[4 * i + 2], ca), st[i].z, st[i].w); f[4 * i + 3] = ln_mod(ln_norm(x[4 * i + 3], cb), st[i].z, st[i].w);
                    }
                    if (s < 13) load(s + 1);
                    stsm4(ha + s * 4096, f[0], f[1], f[2], f[3]); stsm4(ha + s * 4096 + 2048, f[4], f[5], f[6], f[7]);
                };
                float ac[128];
                uint32_t fr[3][8];
                uint64_t bd = (DB128 & ~0xFFFFFFFFull) | mkdesc(sb, DB128);
                reg_def<128>(ac);
                WAIT(B_GFULL + 2 + w, 0);
                load(0);
                prep(0, fr[0]);
                PROFC(17);
#pragma unroll
                for (int s = 0; s < 14; s++) {
                    const uint32_t* f = fr[s % 3];
                    WAIT(B_FULL + g1_slot(s), s >= 7);
                    WG_FENCE();
                    wgmma_rl_256(ac, f[0], f[1], f[2], f[3], bd, s != 0);
                    wgmma_rl_256(ac, f[4], f[5], f[6], f[7], bd + 128, 1);
                    bd += s == 6 ? p.zero - 6 * 1024ull : 1024;
                    WG_COMMIT();
                    if (s < 13) prep(s + 1, fr[(s + 1) % 3]);
                    if (s > 0) { WG_WAIT(1); warp_arrive(BAR(B_EMPTY + g1_slot(s - 1))); }
                }
                fence_async_smem();
                PROFC(18);
                WG_WAIT(0);
                reg_fence<128>(ac);
                warp_arrive(BAR(B_EMPTY + 6));
#pragma unroll
                for (int g = 0; g < 16; g++) {
                    h2a[2 * g] = hmul2(pack2_relu(ac[4 * g], ac[4 * g + 1]), pack2(ac[64 + 4 * g], ac[64 + 4 * g + 1]));
                    h2a[2 * g + 1] = hmul2(pack2_relu(ac[4 * g + 2], ac[4 * g + 3]), pack2(ac[64 + 4 * g + 2], ac[64 + 4 * g + 3]));
                }
                bar_sync(1 + w, 128);
            }
            PROFC(19);
            {
                float ac[64];
                reg_def<64>(ac);
                const uint32_t bx = mkdesc(sb, dconst(8192, 1024, 1));
#pragma unroll 1
                for (int s = 0; s < 7; s++) {
                    WAIT(B_FULL + s, 0);
                    const uint32_t ad = a0 + s * 512, bd = bx + (slot_off(s) >> 4);
                    WG_FENCE();
#pragma unroll
                    for (int k = 0; k < 4; k++) wgmma_ss_128<DT, DB128>(ac, ad + k * 128, bd + k * 128, (s | k) != 0);
                    WG_COMMIT();
                    if (s == 1) {
#pragma unroll
                        for (int g = 0; g < 16; g++) { h2g[(fa / 8 + g) * 512] = h2a[2 * g]; h2g[(fa / 8 + g) * 512 + 32] = h2a[2 * g + 1]; }
                        warp_arrive(BAR(B_PUB + 6));
                    }
                    if (s > 0) { WG_WAIT(1); warp_arrive(BAR(B_EMPTY + s - 1)); }
                }
                WG_WAIT(0);
                reg_fence<64>(ac);
                warp_arrive(BAR(B_EMPTY + 6));
#pragma unroll
                for (int g = 0; g < 8; g++) {
                    h2b[2 * g] = hmul2(pack2_relu(ac[4 * g], ac[4 * g + 1]), pack2(ac[32 + 4 * g], ac[32 + 4 * g + 1]));
                    h2b[2 * g + 1] = hmul2(pack2_relu(ac[4 * g + 2], ac[4 * g + 3]), pack2(ac[32 + 4 * g + 2], ac[32 + 4 * g + 3]));
                }
            }
            PROFC(27);
            {
                float ac[32];
                reg_def<32>(ac);
                const uint32_t bx = mkdesc(sb, dconst(4096, 512, 2));
#pragma unroll 1
                for (int s = 0; s < 7; s++) {
                    WAIT(B_FULL + (s >> 1), 1);
                    const uint32_t ad = a0 + s * 512, bd = bx + s * 512;
                    WG_FENCE();
#pragma unroll
                    for (int k = 0; k < 4; k++) wgmma_ss_64<DT, dconst(4096, 512, 2)>(ac, ad + k * 128, bd + k * 64, (s | k) != 0);
                    WG_COMMIT();
                    if (s == 1) {
#pragma unroll
                        for (int g = 0; g < 8; g++) { h2g[(fb / 8 + g) * 512] = h2b[2 * g]; h2g[(fb / 8 + g) * 512 + 32] = h2b[2 * g + 1]; }
                        warp_arrive(BAR(B_PUB + 7));
                    }
                    if (s > 0 && !(s & 1)) {
                        WG_WAIT(1);
                        __syncwarp();
                        if (lane < 3) mbar_arrive(BAR(B_EMPTY + (s >> 1) - 1 + (lane ? 4 + 3 * lane : 0)));
                    }
                }
                WG_WAIT(0);
                reg_fence<32>(ac);
                PROFC(20);
#pragma unroll
                for (int g = 0; g < 4; g++) {
                    h2b[16 + 2 * g] = hmul2(pack2_relu(ac[4 * g], ac[4 * g + 1]), pack2(ac[16 + 4 * g], ac[16 + 4 * g + 1]));
                    h2b[16 + 2 * g + 1] = hmul2(pack2_relu(ac[4 * g + 2], ac[4 * g + 3]), pack2(ac[16 + 4 * g + 2], ac[16 + 4 * g + 3]));
                    h2g[(fc / 8 + g) * 512] = h2b[16 + 2 * g]; h2g[(fc / 8 + g) * 512 + 32] = h2b[16 + 2 * g + 1];
                }
                warp_arrive(BAR(B_PUB + 8));
                asm volatile("barrier.cluster.wait.aligned;" ::: "memory");
                if (lane == 0) {
                    uint32_t rb;
                    asm volatile("mapa.shared::cluster.u32 %0, %1, %2;" : "=r"(rb) : "r"(BAR(B_PEER)), "r"(kh ^ 1));
                    asm volatile("mbarrier.arrive.relaxed.cluster.shared::cluster.b64 _, [%0];" ::"r"(rb) : "memory");
                }
            }
        }
        PROFC(21);
        {
            float ac[56];
            reg_def<56>(ac);
            constexpr uint64_t DAN = dconst(2048, 128, 0);
            constexpr uint64_t DW = dconst(128, 512, 0);
            const uint32_t bx = mkdesc(sb, DW);
#pragma unroll
            for (int e = 3; e < 7; e++) {
                if (e > 3) WAIT(B_FULL + e, 1);
                const uint64_t bd = ((DW & ~0xFFFFFFFFull) | bx) + (slot_off(e) >> 4);
                const uint32_t* hh = e == 3 ? h2b + 8 : e < 6 ? h2a + 16 * (e - 4) : h2b;
                WG_FENCE();
#pragma unroll
                for (int k = e == 3 ? 2 : 0; k < 4; k++) wgmma_rl_112(ac, hh[4 * k], hh[4 * k + 1], hh[4 * k + 2], hh[4 * k + 3], bd + (k >> 1) * 512 + (k & 1) * 16, e > 3 || k > 2);
                WG_COMMIT();
                if (e > 3) { WG_WAIT(1); warp_arrive(BAR(B_EMPTY + e - 1)); }
            }
            PROFC(22);
            const uint32_t ax = mkdesc(sb + 8192 + w * 1024, DAN);
            uint32_t eb_ = BAR(B_EMPTY + 6);
            uint64_t ord = RING_ORDER;
#pragma unroll 1
            for (int e = 0; e < 21; e++) {
                const uint32_t sl = ord & 15, so = slot_off(sl) >> 4;
                ord = e == 12 ? RING_ORDER : ord >> 4;
                mbar_wait_c(BAR(B_FULL + sl), e >= 13);
                WG_FENCE();
                wgmma_ss_112<DAN, DW>(ac, ax + so, bx + so, 1);
                wgmma_ss_112<DAN, DW>(ac, ax + so + 256, bx + so + 16, 1);
                WG_COMMIT();
                WG_WAIT(1);
                warp_arrive(eb_);
                eb_ = BAR(B_EMPTY + sl);
            }
            mbar_wait_cluster(BAR(B_PEER), 0);
            WG_WAIT(0);
            reg_fence<56>(ac);
            PROFC(24);
            uint32_t rdst, rbar;
            asm volatile("mapa.shared::cluster.u32 %0, %1, %2;" : "=r"(rdst) : "r"(sb + OFF_Y + Y_XCH + w * HALF + t * 16), "r"(kh ^ 1));
            asm volatile("mapa.shared::cluster.u32 %0, %1, %2;" : "=r"(rbar) : "r"(BAR(B_XCH + w)), "r"(kh ^ 1));
#pragma unroll
            for (int g = 0; g < 3; g++)
                asm volatile("st.async.shared::cluster.mbarrier::complete_tx::bytes.v4.b32 [%0], {%1,%2,%3,%4}, [%5];" ::"r"(rdst + g * 2048),
                             "r"(pack2(ac[28 + 8 * g], ac[29 + 8 * g])), "r"(pack2(ac[30 + 8 * g], ac[31 + 8 * g])), "r"(pack2(ac[32 + 8 * g], ac[33 + 8 * g])),
                             "r"(pack2(ac[34 + 8 * g], ac[35 + 8 * g])), "r"(rbar) : "memory");
            asm volatile("st.async.shared::cluster.mbarrier::complete_tx::bytes.v2.b32 [%0], {%1,%2}, [%3];" ::"r"(rdst + 6144 - t * 8),
                         "r"(pack2(ac[52], ac[53])), "r"(pack2(ac[54], ac[55])), "r"(rbar) : "memory");
            mbar_wait_cluster(BAR(B_XCH + w), 0);
            PROFC(25);
            uint32_t op[14], rv[14];
#pragma unroll
            for (int g = 0; g < 3; g++) *(uint4*)(rv + 4 * g) = *(const uint4*)(smem + OFF_Y + Y_XCH + w * HALF + t * 16 + g * 2048);
            *(uint2*)(rv + 12) = *(const uint2*)(smem + OFF_Y + Y_XCH + w * HALF + 6144 + t * 8);
#pragma unroll
            for (int i = 0; i < 14; i++) {
                const float2 gb = *(const float2*)(smem + M_G + 224 + (8 * (i >> 1) + 2 * q) * 4);
                op[i] = pack2(fmaf(gb.x, ac[2 * i] + bf_lo(rv[i]), bf_lo(x1p[i])), fmaf(gb.y, ac[2 * i + 1] + bf_hi(rv[i]), bf_hi(x1p[i])));
            }
            WAIT(B_EMPTY + 4, 1);
            const uint32_t oc = sb + OUT_STAGE + warp * 1792;
            const uint32_t oa = oc + (((lane >> 3) & 1) * 8 + (lane & 7)) * 112 + (lane >> 4) * 16;
            stsm4(oa, op[0], op[1], op[2], op[3]); stsm4(oa + 32, op[4], op[5], op[6], op[7]); stsm4(oa + 64, op[8], op[9], op[10], op[11]);
            asm volatile("stmatrix.sync.aligned.m8n8.x2.shared.b16 [%0], {%1,%2};" ::"r"(oa + 96), "r"(op[12]), "r"(op[13]));
            fence_async_smem();
            __syncwarp();
            asm volatile("{\n.reg .pred p;\nelect.sync _|p, 0xffffffff;\n@p cp.async.bulk.tensor.3d.global.shared::cta.bulk_group [%0, {%2, %3, %4}], [%1];\n"
                         "cp.async.bulk.commit_group;\ncp.async.bulk.wait_group.read 0;\n}" ::"l"(&p.om), "r"(oc), "r"(56 * j), "r"(128 * r + 64 * w + 16 * wi), "r"(0) : "memory");
        }
        PROFC(26);
        bar_sync(1 + w, 128);
        if (wi == 0) warp_arrive(BAR(B_DONE));
        return;
    }
    helper_late(p, r, j, warp PROF_ARGS);
}

#undef act
typedef CUresult (*EncodeFn)(CUtensorMap*, CUtensorMapDataType, cuuint32_t, void*, const cuuint64_t*, const cuuint64_t*, const cuuint32_t*,
                             const cuuint32_t*, CUtensorMapInterleave, CUtensorMapSwizzle, CUtensorMapL2promotion, CUtensorMapFloatOOBfill);

static void make_map(EncodeFn fn, CUtensorMap* m, const void* ptr, uint64_t d0, uint64_t d1, uint64_t d2, uint64_t s1, uint64_t s2,
                     uint32_t b0, uint32_t b1, uint32_t b2, CUtensorMapSwizzle sw) {
    cuuint64_t dims[3] = {d0, d1, d2}, strides[2] = {s1, s2};
    cuuint32_t box[3] = {b0, b1, b2}, es[3] = {1, 1, 1};
    CUresult rc = fn(m, CU_TENSOR_MAP_DATA_TYPE_BFLOAT16, 3, (void*)ptr, dims, strides, box, es, CU_TENSOR_MAP_INTERLEAVE_NONE, sw,
                     CU_TENSOR_MAP_L2_PROMOTION_L2_128B, CU_TENSOR_MAP_FLOAT_OOB_FILL_NONE);
    (void)rc;
}

extern "C" void kernel_launch(void* const* d_in, const int* in_sizes, int n_in, void* d_out, int out_size) {
    (void)in_sizes; (void)n_in; (void)out_size;
    static EncodeFn fn = nullptr;
    static uint32_t* act_base = nullptr;
    if (!fn) {
        cudaDriverEntryPointQueryResult st;
        cudaGetDriverEntryPoint("cuTensorMapEncodeTiled", (void**)&fn, cudaEnableDefault, &st);
        void* a = nullptr;
        cudaGetSymbolAddress(&a, g_act);
        act_base = (uint32_t*)(((uintptr_t)a + 0xFFFFF) & ~(uintptr_t)0xFFFFF);
        cudaFuncSetAttribute(fused_block_kernel, cudaFuncAttributeMaxDynamicSharedMemorySize, SMEM_BYTES);
    }
    Params p;
    p.x = (const bf16*)d_in[0];
    const bf16* wqkv = (const bf16*)d_in[1];
    p.wqkv = wqkv;
    p.wop = (const bf16*)d_in[2];
    p.wg = (const bf16*)d_in[4];
    p.wu = (const bf16*)d_in[5];
    p.wd = (const bf16*)d_in[6];
    p.c = (const bf16*)d_in[7];
    p.wmod = (const bf16*)d_in[8];
    p.out = (bf16*)d_out;
    p.zero = 0;
    p.actb = act_base;
    make_map(fn, &p.wm, p.wmod, 2688, 448, 1, 5376, 5376 * 448, 16, 224, 1, CU_TENSOR_MAP_SWIZZLE_NONE);
    make_map(fn, &p.wm2, p.wmod, 2688, 448, 1, 5376, 5376 * 448, 32, 224, 1, CU_TENSOR_MAP_SWIZZLE_NONE);
    make_map(fn, &p.om, p.out, 448, 2048, 1, 896, 896 * 2048, 56, 16, 1, CU_TENSOR_MAP_SWIZZLE_NONE);
    make_map(fn, &p.xm, p.x, 448, 2048, 1, 896, 896 * 2048, 64, 128, 1, CU_TENSOR_MAP_SWIZZLE_128B);
    make_map(fn, &p.qkv, wqkv, 1344, 448, 1, 2688, 2688 * 448, 64, 224, 1, CU_TENSOR_MAP_SWIZZLE_128B);
    make_map(fn, &p.wo, p.wop, 448, 448, 1, 896, 896 * 448, 64, 224, 1, CU_TENSOR_MAP_SWIZZLE_128B);
    make_map(fn, &p.ga, p.wg, 64, 448, 28, 3584, 128, 64, 32, 2, CU_TENSOR_MAP_SWIZZLE_128B);
    make_map(fn, &p.ua, p.wu, 64, 448, 28, 3584, 128, 64, 32, 2, CU_TENSOR_MAP_SWIZZLE_128B);
    make_map(fn, &p.gb, p.wg, 64, 448, 28, 3584, 128, 64, 64, 1, CU_TENSOR_MAP_SWIZZLE_128B);
    make_map(fn, &p.ub, p.wu, 64, 448, 28, 3584, 128, 64, 64, 1, CU_TENSOR_MAP_SWIZZLE_128B);
    make_map(fn, &p.gc, p.wg, 32, 448, 56, 3584, 64, 32, 64, 1, CU_TENSOR_MAP_SWIZZLE_64B);
    make_map(fn, &p.uc, p.wu, 32, 448, 56, 3584, 64, 32, 64, 1, CU_TENSOR_MAP_SWIZZLE_64B);
    make_map(fn, &p.dn, p.wd, 8, 1792, 56, 896, 16, 8, 32, 7, CU_TENSOR_MAP_SWIZZLE_NONE);
    fused_block_kernel<<<NCTA, 384, SMEM_BYTES>>>(p);
}
```

```cpp
#include <cuda_runtime.h>
#include <cuda_bf16.h>
#include <cuda.h>
#include <stdint.h>

typedef __nv_bfloat16 bf16;

template<uint64_t CA, uint64_t CB> __device__ __forceinline__ void wgmma_sk_160(float* d, uint32_t da, uint32_t db, int sd) {
  asm volatile("{\n.reg .pred p;\n.reg .b64 a, b;\nsetp.ne.b32 p, %82, 0;\nmov.b64 a, {%80, %83};\nmov.b64 b, {%81, %84};\n"
    "wgmma.mma_async.sync.aligned.m64n160k16.f32.bf16.bf16 {%0,%1,%2,%3,%4,%5,%6,%7,%8,%9,%10,%11,%12,%13,%14,%15,%16,%17,%18,%19,%20,%21,%22,%23,%24,%25,%26,%27,%28,%29,%30,%31,%32,%33,%34,%35,%36,%37,%38,%39,%40,%41,%42,%43,%44,%45,%46,%47,%48,%49,%50,%51,%52,%53,%54,%55,%56,%57,%58,%59,%60,%61,%62,%63,%64,%65,%66,%67,%68,%69,%70,%71,%72,%73,%74,%75,%76,%77,%78,%79}, a, b, p, 1, 1, 0, 0;\n}\n"
    : "+f"(d[0]),"+f"(d[1]),"+f"(d[2]),"+f"(d[3]),"+f"(d[4]),"+f"(d[5]),"+f"(d[6]),"+f"(d[7]),"+f"(d[8]),"+f"(d[9]),"+f"(d[10]),"+f"(d[11]),"+f"(d[12]),"+f"(d[13]),"+f"(d[14]),"+f"(d[15]),"+f"(d[16]),"+f"(d[17]),"+f"(d[18]),"+f"(d[19]),"+f"(d[20]),"+f"(d[21]),"+f"(d[22]),"+f"(d[23]),"+f"(d[24]),"+f"(d[25]),"+f"(d[26]),"+f"(d[27]),"+f"(d[28]),"+f"(d[29]),"+f"(d[30]),"+f"(d[31]),"+f"(d[32]),"+f"(d[33]),"+f"(d[34]),"+f"(d[35]),"+f"(d[36]),"+f"(d[37]),"+f"(d[38]),"+f"(d[39]),"+f"(d[40]),"+f"(d[41]),"+f"(d[42]),"+f"(d[43]),"+f"(d[44]),"+f"(d[45]),"+f"(d[46]),"+f"(d[47]),"+f"(d[48]),"+f"(d[49]),"+f"(d[50]),"+f"(d[51]),"+f"(d[52]),"+f"(d[53]),"+f"(d[54]),"+f"(d[55]),"+f"(d[56]),"+f"(d[57]),"+f"(d[58]),"+f"(d[59]),"+f"(d[60]),"+f"(d[61]),"+f"(d[62]),"+f"(d[63]),"+f"(d[64]),"+f"(d[65]),"+f"(d[66]),"+f"(d[67]),"+f"(d[68]),"+f"(d[69]),"+f"(d[70]),"+f"(d[71]),"+f"(d[72]),"+f"(d[73]),"+f"(d[74]),"+f"(d[75]),"+f"(d[76]),"+f"(d[77]),"+f"(d[78]),"+f"(d[79])
    : "r"(da), "r"(db), "r"(sd), "n"((uint32_t)(CA >> 32)), "n"((uint32_t)(CB >> 32)));
}
__device__ __forceinline__ void wgmma_rl_56(float* d, uint32_t a0, uint32_t a1, uint32_t a2, uint32_t a3, uint64_t db, int sd) {
  asm volatile("{\n.reg .pred p;\nsetp.ne.b32 p, %33, 0;\n"
    "wgmma.mma_async.sync.aligned.m64n56k16.f32.bf16.bf16 {%0,%1,%2,%3,%4,%5,%6,%7,%8,%9,%10,%11,%12,%13,%14,%15,%16,%17,%18,%19,%20,%21,%22,%23,%24,%25,%26,%27}, {%28,%29,%30,%31}, %32, p, 1, 1, 1;\n}\n"
    : "+f"(d[0]),"+f"(d[1]),"+f"(d[2]),"+f"(d[3]),"+f"(d[4]),"+f"(d[5]),"+f"(d[6]),"+f"(d[7]),"+f"(d[8]),"+f"(d[9]),"+f"(d[10]),"+f"(d[11]),"+f"(d[12]),"+f"(d[13]),"+f"(d[14]),"+f"(d[15]),"+f"(d[16]),"+f"(d[17]),"+f"(d[18]),"+f"(d[19]),"+f"(d[20]),"+f"(d[21]),"+f"(d[22]),"+f"(d[23]),"+f"(d[24]),"+f"(d[25]),"+f"(d[26]),"+f"(d[27])
    : "r"(a0), "r"(a1), "r"(a2), "r"(a3), "l"(db), "r"(sd));
}
template<uint64_t CA, uint64_t CB> __device__ __forceinline__ void wgmma_ss_56(float* d, uint32_t da, uint32_t db, int sd) {
  asm volatile("{\n.reg .pred p;\n.reg .b64 a, b;\nsetp.ne.b32 p, %30, 0;\nmov.b64 a, {%28, %31};\nmov.b64 b, {%29, %32};\n"
    "wgmma.mma_async.sync.aligned.m64n56k16.f32.bf16.bf16 {%0,%1,%2,%3,%4,%5,%6,%7,%8,%9,%10,%11,%12,%13,%14,%15,%16,%17,%18,%19,%20,%21,%22,%23,%24,%25,%26,%27}, a, b, p, 1, 1, 0, 1;\n}\n"
    : "+f"(d[0]),"+f"(d[1]),"+f"(d[2]),"+f"(d[3]),"+f"(d[4]),"+f"(d[5]),"+f"(d[6]),"+f"(d[7]),"+f"(d[8]),"+f"(d[9]),"+f"(d[10]),"+f"(d[11]),"+f"(d[12]),"+f"(d[13]),"+f"(d[14]),"+f"(d[15]),"+f"(d[16]),"+f"(d[17]),"+f"(d[18]),"+f"(d[19]),"+f"(d[20]),"+f"(d[21]),"+f"(d[22]),"+f"(d[23]),"+f"(d[24]),"+f"(d[25]),"+f"(d[26]),"+f"(d[27])
    : "r"(da), "r"(db), "r"(sd), "n"((uint32_t)(CA >> 32)), "n"((uint32_t)(CB >> 32)));
}
__device__ __forceinline__ void wgmma_rl_256(float* d, uint32_t a0, uint32_t a1, uint32_t a2, uint32_t a3, uint64_t db, int sd) {
  asm volatile("{\n.reg .pred p;\nsetp.ne.b32 p, %133, 0;\n"
    "wgmma.mma_async.sync.aligned.m64n256k16.f32.bf16.bf16 {%0,%1,%2,%3,%4,%5,%6,%7,%8,%9,%10,%11,%12,%13,%14,%15,%16,%17,%18,%19,%20,%21,%22,%23,%24,%25,%26,%27,%28,%29,%30,%31,%32,%33,%34,%35,%36,%37,%38,%39,%40,%41,%42,%43,%44,%45,%46,%47,%48,%49,%50,%51,%52,%53,%54,%55,%56,%57,%58,%59,%60,%61,%62,%63,%64,%65,%66,%67,%68,%69,%70,%71,%72,%73,%74,%75,%76,%77,%78,%79,%80,%81,%82,%83,%84,%85,%86,%87,%88,%89,%90,%91,%92,%93,%94,%95,%96,%97,%98,%99,%100,%101,%102,%103,%104,%105,%106,%107,%108,%109,%110,%111,%112,%113,%114,%115,%116,%117,%118,%119,%120,%121,%122,%123,%124,%125,%126,%127}, {%128,%129,%130,%131}, %132, p, 1, 1, 1;\n}\n"
    : "+f"(d[0]),"+f"(d[1]),"+f"(d[2]),"+f"(d[3]),"+f"(d[4]),"+f"(d[5]),"+f"(d[6]),"+f"(d[7]),"+f"(d[8]),"+f"(d[9]),"+f"(d[10]),"+f"(d[11]),"+f"(d[12]),"+f"(d[13]),"+f"(d[14]),"+f"(d[15]),"+f"(d[16]),"+f"(d[17]),"+f"(d[18]),"+f"(d[19]),"+f"(d[20]),"+f"(d[21]),"+f"(d[22]),"+f"(d[23]),"+f"(d[24]),"+f"(d[25]),"+f"(d[26]),"+f"(d[27]),"+f"(d[28]),"+f"(d[29]),"+f"(d[30]),"+f"(d[31]),"+f"(d[32]),"+f"(d[33]),"+f"(d[34]),"+f"(d[35]),"+f"(d[36]),"+f"(d[37]),"+f"(d[38]),"+f"(d[39]),"+f"(d[40]),"+f"(d[41]),"+f"(d[42]),"+f"(d[43]),"+f"(d[44]),"+f"(d[45]),"+f"(d[46]),"+f"(d[47]),"+f"(d[48]),"+f"(d[49]),"+f"(d[50]),"+f"(d[51]),"+f"(d[52]),"+f"(d[53]),"+f"(d[54]),"+f"(d[55]),"+f"(d[56]),"+f"(d[57]),"+f"(d[58]),"+f"(d[59]),"+f"(d[60]),"+f"(d[61]),"+f"(d[62]),"+f"(d[63]),"+f"(d[64]),"+f"(d[65]),"+f"(d[66]),"+f"(d[67]),"+f"(d[68]),"+f"(d[69]),"+f"(d[70]),"+f"(d[71]),"+f"(d[72]),"+f"(d[73]),"+f"(d[74]),"+f"(d[75]),"+f"(d[76]),"+f"(d[77]),"+f"(d[78]),"+f"(d[79]),"+f"(d[80]),"+f"(d[81]),"+f"(d[82]),"+f"(d[83]),"+f"(d[84]),"+f"(d[85]),"+f"(d[86]),"+f"(d[87]),"+f"(d[88]),"+f"(d[89]),"+f"(d[90]),"+f"(d[91]),"+f"(d[92]),"+f"(d[93]),"+f"(d[94]),"+f"(d[95]),"+f"(d[96]),"+f"(d[97]),"+f"(d[98]),"+f"(d[99]),"+f"(d[100]),"+f"(d[101]),"+f"(d[102]),"+f"(d[103]),"+f"(d[104]),"+f"(d[105]),"+f"(d[106]),"+f"(d[107]),"+f"(d[108]),"+f"(d[109]),"+f"(d[110]),"+f"(d[111]),"+f"(d[112]),"+f"(d[113]),"+f"(d[114]),"+f"(d[115]),"+f"(d[116]),"+f"(d[117]),"+f"(d[118]),"+f"(d[119]),"+f"(d[120]),"+f"(d[121]),"+f"(d[122]),"+f"(d[123]),"+f"(d[124]),"+f"(d[125]),"+f"(d[126]),"+f"(d[127])
    : "r"(a0), "r"(a1), "r"(a2), "r"(a3), "l"(db), "r"(sd));
}
template<uint64_t CA, uint64_t CB> __device__ __forceinline__ void wgmma_ss_128(float* d, uint32_t da, uint32_t db, int sd) {
  asm volatile("{\n.reg .pred p;\n.reg .b64 a, b;\nsetp.ne.b32 p, %66, 0;\nmov.b64 a, {%64, %67};\nmov.b64 b, {%65, %68};\n"
    "wgmma.mma_async.sync.aligned.m64n128k16.f32.bf16.bf16 {%0,%1,%2,%3,%4,%5,%6,%7,%8,%9,%10,%11,%12,%13,%14,%15,%16,%17,%18,%19,%20,%21,%22,%23,%24,%25,%26,%27,%28,%29,%30,%31,%32,%33,%34,%35,%36,%37,%38,%39,%40,%41,%42,%43,%44,%45,%46,%47,%48,%49,%50,%51,%52,%53,%54,%55,%56,%57,%58,%59,%60,%61,%62,%63}, a, b, p, 1, 1, 0, 1;\n}\n"
    : "+f"(d[0]),"+f"(d[1]),"+f"(d[2]),"+f"(d[3]),"+f"(d[4]),"+f"(d[5]),"+f"(d[6]),"+f"(d[7]),"+f"(d[8]),"+f"(d[9]),"+f"(d[10]),"+f"(d[11]),"+f"(d[12]),"+f"(d[13]),"+f"(d[14]),"+f"(d[15]),"+f"(d[16]),"+f"(d[17]),"+f"(d[18]),"+f"(d[19]),"+f"(d[20]),"+f"(d[21]),"+f"(d[22]),"+f"(d[23]),"+f"(d[24]),"+f"(d[25]),"+f"(d[26]),"+f"(d[27]),"+f"(d[28]),"+f"(d[29]),"+f"(d[30]),"+f"(d[31]),"+f"(d[32]),"+f"(d[33]),"+f"(d[34]),"+f"(d[35]),"+f"(d[36]),"+f"(d[37]),"+f"(d[38]),"+f"(d[39]),"+f"(d[40]),"+f"(d[41]),"+f"(d[42]),"+f"(d[43]),"+f"(d[44]),"+f"(d[45]),"+f"(d[46]),"+f"(d[47]),"+f"(d[48]),"+f"(d[49]),"+f"(d[50]),"+f"(d[51]),"+f"(d[52]),"+f"(d[53]),"+f"(d[54]),"+f"(d[55]),"+f"(d[56]),"+f"(d[57]),"+f"(d[58]),"+f"(d[59]),"+f"(d[60]),"+f"(d[61]),"+f"(d[62]),"+f"(d[63])
    : "r"(da), "r"(db), "r"(sd), "n"((uint32_t)(CA >> 32)), "n"((uint32_t)(CB >> 32)));
}
template<uint64_t CA, uint64_t CB> __device__ __forceinline__ void wgmma_ss_64(float* d, uint32_t da, uint32_t db, int sd) {
  asm volatile("{\n.reg .pred p;\n.reg .b64 a, b;\nsetp.ne.b32 p, %34, 0;\nmov.b64 a, {%32, %35};\nmov.b64 b, {%33, %36};\n"
    "wgmma.mma_async.sync.aligned.m64n64k16.f32.bf16.bf16 {%0,%1,%2,%3,%4,%5,%6,%7,%8,%9,%10,%11,%12,%13,%14,%15,%16,%17,%18,%19,%20,%21,%22,%23,%24,%25,%26,%27,%28,%29,%30,%31}, a, b, p, 1, 1, 0, 1;\n}\n"
    : "+f"(d[0]),"+f"(d[1]),"+f"(d[2]),"+f"(d[3]),"+f"(d[4]),"+f"(d[5]),"+f"(d[6]),"+f"(d[7]),"+f"(d[8]),"+f"(d[9]),"+f"(d[10]),"+f"(d[11]),"+f"(d[12]),"+f"(d[13]),"+f"(d[14]),"+f"(d[15]),"+f"(d[16]),"+f"(d[17]),"+f"(d[18]),"+f"(d[19]),"+f"(d[20]),"+f"(d[21]),"+f"(d[22]),"+f"(d[23]),"+f"(d[24]),"+f"(d[25]),"+f"(d[26]),"+f"(d[27]),"+f"(d[28]),"+f"(d[29]),"+f"(d[30]),"+f"(d[31])
    : "r"(da), "r"(db), "r"(sd), "n"((uint32_t)(CA >> 32)), "n"((uint32_t)(CB >> 32)));
}
template<uint64_t CA, uint64_t CB> __device__ __forceinline__ void wgmma_ss_112(float* d, uint32_t da, uint32_t db, int sd) {
  asm volatile("{\n.reg .pred p;\n.reg .b64 a, b;\nsetp.ne.b32 p, %58, 0;\nmov.b64 a, {%56, %59};\nmov.b64 b, {%57, %60};\n"
    "wgmma.mma_async.sync.aligned.m64n112k16.f32.bf16.bf16 {%0,%1,%2,%3,%4,%5,%6,%7,%8,%9,%10,%11,%12,%13,%14,%15,%16,%17,%18,%19,%20,%21,%22,%23,%24,%25,%26,%27,%28,%29,%30,%31,%32,%33,%34,%35,%36,%37,%38,%39,%40,%41,%42,%43,%44,%45,%46,%47,%48,%49,%50,%51,%52,%53,%54,%55}, a, b, p, 1, 1, 0, 1;\n}\n"
    : "+f"(d[0]),"+f"(d[1]),"+f"(d[2]),"+f"(d[3]),"+f"(d[4]),"+f"(d[5]),"+f"(d[6]),"+f"(d[7]),"+f"(d[8]),"+f"(d[9]),"+f"(d[10]),"+f"(d[11]),"+f"(d[12]),"+f"(d[13]),"+f"(d[14]),"+f"(d[15]),"+f"(d[16]),"+f"(d[17]),"+f"(d[18]),"+f"(d[19]),"+f"(d[20]),"+f"(d[21]),"+f"(d[22]),"+f"(d[23]),"+f"(d[24]),"+f"(d[25]),"+f"(d[26]),"+f"(d[27]),"+f"(d[28]),"+f"(d[29]),"+f"(d[30]),"+f"(d[31]),"+f"(d[32]),"+f"(d[33]),"+f"(d[34]),"+f"(d[35]),"+f"(d[36]),"+f"(d[37]),"+f"(d[38]),"+f"(d[39]),"+f"(d[40]),"+f"(d[41]),"+f"(d[42]),"+f"(d[43]),"+f"(d[44]),"+f"(d[45]),"+f"(d[46]),"+f"(d[47]),"+f"(d[48]),"+f"(d[49]),"+f"(d[50]),"+f"(d[51]),"+f"(d[52]),"+f"(d[53]),"+f"(d[54]),"+f"(d[55])
    : "r"(da), "r"(db), "r"(sd), "n"((uint32_t)(CA >> 32)), "n"((uint32_t)(CB >> 32)));
}
__device__ __forceinline__ void wgmma_rl_112(float* d, uint32_t a0, uint32_t a1, uint32_t a2, uint32_t a3, uint64_t db, int sd) {
  asm volatile("{\n.reg .pred p;\nsetp.ne.b32 p, %61, 0;\n"
    "wgmma.mma_async.sync.aligned.m64n112k16.f32.bf16.bf16 {%0,%1,%2,%3,%4,%5,%6,%7,%8,%9,%10,%11,%12,%13,%14,%15,%16,%17,%18,%19,%20,%21,%22,%23,%24,%25,%26,%27,%28,%29,%30,%31,%32,%33,%34,%35,%36,%37,%38,%39,%40,%41,%42,%43,%44,%45,%46,%47,%48,%49,%50,%51,%52,%53,%54,%55}, {%56,%57,%58,%59}, %60, p, 1, 1, 1;\n}\n"
    : "+f"(d[0]),"+f"(d[1]),"+f"(d[2]),"+f"(d[3]),"+f"(d[4]),"+f"(d[5]),"+f"(d[6]),"+f"(d[7]),"+f"(d[8]),"+f"(d[9]),"+f"(d[10]),"+f"(d[11]),"+f"(d[12]),"+f"(d[13]),"+f"(d[14]),"+f"(d[15]),"+f"(d[16]),"+f"(d[17]),"+f"(d[18]),"+f"(d[19]),"+f"(d[20]),"+f"(d[21]),"+f"(d[22]),"+f"(d[23]),"+f"(d[24]),"+f"(d[25]),"+f"(d[26]),"+f"(d[27]),"+f"(d[28]),"+f"(d[29]),"+f"(d[30]),"+f"(d[31]),"+f"(d[32]),"+f"(d[33]),"+f"(d[34]),"+f"(d[35]),"+f"(d[36]),"+f"(d[37]),"+f"(d[38]),"+f"(d[39]),"+f"(d[40]),"+f"(d[41]),"+f"(d[42]),"+f"(d[43]),"+f"(d[44]),"+f"(d[45]),"+f"(d[46]),"+f"(d[47]),"+f"(d[48]),"+f"(d[49]),"+f"(d[50]),"+f"(d[51]),"+f"(d[52]),"+f"(d[53]),"+f"(d[54]),"+f"(d[55])
    : "r"(a0), "r"(a1), "r"(a2), "r"(a3), "l"(db), "r"(sd));
}

constexpr int DM = 448;
constexpr int NCTA = 128;
#define WIN 5
#define NPRE 14
#define VPRE 3
constexpr int SPIN_LIMIT = 1 << 22;

constexpr uint32_t OFF_X = 0, OFF_Y = 114688, OFF_MISC = 229376, SMEM_BYTES = 232448;
constexpr uint32_t Y_VR = 0, Y_K = 28672, Y_KOWN = 57344, Y_VOWN = 71680, Y_Q = 86016;
constexpr uint32_t HALF = 57344;
constexpr uint32_t X_STAT = 49152;
constexpr uint32_t OUT_STAGE = 4 * 16384;
constexpr uint32_t M_BAR = OFF_MISC;
constexpr uint32_t M_ST = OFF_MISC + 512;
constexpr uint32_t M_G = OFF_MISC + 2304;
constexpr uint32_t M_EPOCH = OFF_MISC + 3040;
enum { B_XFULL = 0, B_FULLK = 7, B_FULLV = 8, B_FULLQ, B_KRFULL, B_VRFULL, B_WOFULL, B_XCH, B_MOD1 = 15, B_FULL = 16, B_WMFULL = 30,
       B_EMPTY = 32, B_PEER = 45, B_EPOCH,
       B_PUB = 47,
       B_XFREE = B_PUB + 4, B_GEMV,
       B_WMFREE = 56, B_HRDY, B_GFULL = B_HRDY + 3, B_DONE = 31 };

__device__ uint32_t g_ticket;
__device__ __align__(128) uint32_t g_mod[8 * 6 * DM];
__device__ __align__(128) uint32_t g_flag[144 * 192];
constexpr int RB_WORDS = 262144, RB_KV = 0, RB_O = 57344, RB_X1 = 86016, RB_H2 = 143360, RB_ST = 258048;
__device__ __align__(128) uint32_t g_act[17 * RB_WORDS];
__device__ __align__(128) uint32_t g_wd[56 * 4 * 1792];
#define PROFH(id)
#define PROFH1(id)
#define PROFC(id)

struct alignas(64) Params {
    CUtensorMap wm, wm2, om, xm, qkv, wo, ga, ua, gb, ub, gc, uc, dn;
    const bf16 *x, *c, *wqkv, *wmod, *wg, *wu, *wd, *wop;
    bf16* out;
    uint32_t* actb;
    uint32_t zero;
};

__device__ __forceinline__ void mbar_init(uint32_t bar, int cnt) { asm volatile("mbarrier.init.shared::cta.b64 [%0], %1;" ::"r"(bar), "r"(cnt) : "memory"); }
__device__ __forceinline__ void mbar_arrive(uint32_t bar) { asm volatile("mbarrier.arrive.shared::cta.b64 _, [%0];" ::"r"(bar) : "memory"); }
__device__ __forceinline__ void mbar_wait(uint32_t bar, uint32_t parity) {
    uint32_t ok; int n = 0;
    do {
        asm volatile("{\n.reg .pred p;\nmbarrier.try_wait.parity.shared::cta.b64 p, [%1], %2;\nselp.u32 %0, 1, 0, p;\n}" : "=r"(ok) : "r"(bar), "r"(parity) : "memory");
        if (++n > SPIN_LIMIT) __trap();
    } while (!ok);
}
__device__ __forceinline__ void mbar_wait_c(uint32_t bar, uint32_t parity) {
    asm volatile("{\n.reg .pred p;\nWL:\nmbarrier.try_wait.parity.shared::cta.b64 p, [%0], %1, 0x989680;\n@!p bra WL;\n}" ::"r"(bar), "r"(parity) : "memory");
}
__device__ __forceinline__ void mbar_wait_cluster(uint32_t bar, uint32_t parity) {
    asm volatile("{\n.reg .pred p;\nWL:\nmbarrier.try_wait.parity.acquire.cluster.shared::cta.b64 p, [%0], %1, 0x989680;\n@!p bra WL;\n}" ::"r"(bar), "r"(parity) : "memory");
}
__device__ __forceinline__ void warp_arrive(uint32_t bar) {
    __syncwarp();
    asm volatile("{\n.reg .pred p;\nelect.sync _|p, 0xffffffff;\n@p mbarrier.arrive.shared::cta.b64 _, [%0];\n}" ::"r"(bar) : "memory");
}
__device__ __forceinline__ int opaque(int v) { return __shfl_sync(~0u, v, 0); }
__device__ __forceinline__ int fresh_tid() { int v; asm volatile("mov.u32 %0, %%tid.x;" : "=r"(v)); return v; }
__device__ __forceinline__ void bar_sync(int id, int n) { asm volatile("bar.sync %0, %1;" ::"r"(id), "r"(n) : "memory"); }
__device__ __forceinline__ void bar_arrive(int id, int n) { asm volatile("bar.arrive %0, %1;" ::"r"(id), "r"(n) : "memory"); }
__device__ __forceinline__ void fence_async_smem() { asm volatile("fence.proxy.async.shared::cta;" ::: "memory"); }
__device__ __forceinline__ void fence_async_global() { asm volatile("fence.proxy.async.global;" ::: "memory"); }
__device__ __forceinline__ void fence_gpu() { asm volatile("fence.release.gpu;" ::: "memory"); }
__device__ __forceinline__ void expect_e(uint32_t bar, uint32_t bytes) {
    asm volatile("{\n.reg .pred p;\nelect.sync _|p, 0xffffffff;\n@p mbarrier.arrive.expect_tx.shared::cta.b64 _, [%0], %1;\n}" ::"r"(bar), "r"(bytes) : "memory");
}
__device__ __forceinline__ void tma3_e(uint32_t dst, const CUtensorMap* m, int c0, int c1, int c2, uint32_t bar) {
    asm volatile("{\n.reg .pred p;\nelect.sync _|p, 0xffffffff;\n@p cp.async.bulk.tensor.3d.shared::cluster.global.mbarrier::complete_tx::bytes [%0], [%1, {%3, %4, %5}], [%2];\n}"
                 ::"r"(dst), "l"(m), "r"(bar), "r"(c0), "r"(c1), "r"(c2) : "memory");
}
__device__ __forceinline__ void bulk_e(uint32_t dst, const void* src, uint32_t bytes, uint32_t bar) {
    asm volatile("{\n.reg .pred p;\nelect.sync _|p, 0xffffffff;\n@p cp.async.bulk.shared::cluster.global.mbarrier::complete_tx::bytes [%0], [%1], %2, [%3];\n}"
                 ::"r"(dst), "l"(src), "r"(bytes), "r"(bar) : "memory");
}
__device__ __forceinline__ void init_e(uint32_t bar, int cnt) {
    asm volatile("{\n.reg .pred p;\nelect.sync _|p, 0xffffffff;\n@p mbarrier.init.shared::cta.b64 [%0], %1;\n}" ::"r"(bar), "r"(cnt) : "memory");
}
__device__ __forceinline__ void l2_prefetch_e(const void* src, uint32_t bytes) {
    asm volatile("{\n.reg .pred p;\nelect.sync _|p, 0xffffffff;\n@p cp.async.bulk.prefetch.L2.global [%0], %1;\n}" ::"l"(src), "r"(bytes) : "memory");
}
__device__ __forceinline__ uint32_t ld_relaxed(const uint32_t* p) { uint32_t v; asm volatile("ld.relaxed.gpu.global.u32 %0, [%1];" : "=r"(v) : "l"(p) : "memory"); return v; }
__device__ __forceinline__ void st_relaxed(uint32_t* p, uint32_t v) { asm volatile("st.relaxed.gpu.global.u32 [%0], %1;" ::"l"(p), "r"(v) : "memory"); }
__device__ __forceinline__ uint4 ld_relaxed4(const uint4* p) { uint4 v; asm volatile("ld.relaxed.gpu.global.v4.u32 {%0,%1,%2,%3}, [%4];" : "=r"(v.x), "=r"(v.y), "=r"(v.z), "=r"(v.w) : "l"(p) : "memory"); return v; }
__device__ __forceinline__ uint4 lds4(uint32_t a) { uint4 v; asm volatile("ld.shared.v4.u32 {%0,%1,%2,%3}, [%4];" : "=r"(v.x), "=r"(v.y), "=r"(v.z), "=r"(v.w) : "r"(a) : "memory"); return v; }
__device__ __forceinline__ float2 lds2f(uint32_t a) { float2 v; asm volatile("ld.shared.v2.f32 {%0,%1}, [%2];" : "=f"(v.x), "=f"(v.y) : "r"(a) : "memory"); return v; }
__device__ __forceinline__ uint32_t lds1(uint32_t a) { uint32_t v; asm volatile("ld.shared.u32 %0, [%1];" : "=r"(v) : "r"(a) : "memory"); return v; }
__device__ __forceinline__ void sts4(uint32_t a, uint4 v) { asm volatile("st.shared.v4.u32 [%0], {%1,%2,%3,%4};" ::"r"(a), "r"(v.x), "r"(v.y), "r"(v.z), "r"(v.w) : "memory"); }
__device__ __forceinline__ void sts1(uint32_t a, uint32_t v) { asm volatile("st.shared.u32 [%0], %1;" ::"r"(a), "r"(v) : "memory"); }
__device__ __forceinline__ void stsm4(uint32_t a, uint32_t r0, uint32_t r1, uint32_t r2, uint32_t r3) {
    asm volatile("stmatrix.sync.aligned.m8n8.x4.shared.b16 [%0], {%1,%2,%3,%4};" ::"r"(a), "r"(r0), "r"(r1), "r"(r2), "r"(r3));
}
__device__ __forceinline__ uint32_t pack2(float lo, float hi) { uint32_t r; asm("cvt.rn.bf16x2.f32 %0, %1, %2;" : "=r"(r) : "f"(hi), "f"(lo)); return r; }
__device__ __forceinline__ uint32_t pack2_relu(float lo, float hi) { uint32_t r; asm("cvt.rn.relu.bf16x2.f32 %0, %1, %2;" : "=r"(r) : "f"(hi), "f"(lo)); return r; }
__device__ __forceinline__ uint32_t hfma2(uint32_t a, uint32_t b, uint32_t c) { uint32_t r; asm("fma.rn.bf16x2 %0, %1, %2, %3;" : "=r"(r) : "r"(a), "r"(b), "r"(c)); return r; }
__device__ __forceinline__ uint32_t hmul2(uint32_t a, uint32_t b) { uint32_t r; asm("mul.rn.bf16x2 %0, %1, %2;" : "=r"(r) : "r"(a), "r"(b)); return r; }
__device__ __forceinline__ float bf_lo(uint32_t v) { return __uint_as_float(v << 16); }
__device__ __forceinline__ float bf_hi(uint32_t v) { return __uint_as_float(v & 0xFFFF0000u); }
__device__ __forceinline__ float bf_round(float v) { return bf_lo(pack2(v, 0.f)); }
__device__ __forceinline__ float ex2(float x) { float r; asm("ex2.approx.ftz.f32 %0, %1;" : "=f"(r) : "f"(x)); return r; }
__device__ __forceinline__ void mma16816(float* d, uint32_t a0, uint32_t a1, uint32_t a2, uint32_t a3, uint32_t b0, uint32_t b1) {
    asm("mma.sync.aligned.m16n8k16.row.col.f32.bf16.bf16.f32 {%0,%1,%2,%3}, {%4,%5,%6,%7}, {%8,%9}, {%0,%1,%2,%3};"
        : "+f"(d[0]), "+f"(d[1]), "+f"(d[2]), "+f"(d[3]) : "r"(a0), "r"(a1), "r"(a2), "r"(a3), "r"(b0), "r"(b1));
}
__device__ __forceinline__ void mma1688(float* d, uint32_t a0, uint32_t a1, uint32_t b0) {
    asm("mma.sync.aligned.m16n8k8.row.col.f32.bf16.bf16.f32 {%0,%1,%2,%3}, {%4,%5}, {%6}, {%0,%1,%2,%3};"
        : "+f"(d[0]), "+f"(d[1]), "+f"(d[2]), "+f"(d[3]) : "r"(a0), "r"(a1), "r"(b0));
}
__device__ __forceinline__ void ldsm4(uint32_t a, uint32_t* r) {
    asm volatile("ldmatrix.sync.aligned.m8n8.x4.shared.b16 {%0,%1,%2,%3}, [%4];" : "=r"(r[0]), "=r"(r[1]), "=r"(r[2]), "=r"(r[3]) : "r"(a));
}
__device__ __forceinline__ void ldsm4t(uint32_t a, uint32_t* r) {
    asm volatile("ldmatrix.sync.aligned.m8n8.x4.trans.shared.b16 {%0,%1,%2,%3}, [%4];" : "=r"(r[0]), "=r"(r[1]), "=r"(r[2]), "=r"(r[3]) : "r"(a));
}
__device__ __forceinline__ uint32_t nz(uint32_t v) { uint32_t r; asm("max.u32 %0, %1, 1;" : "=r"(r) : "r"(v)); return r; }
__device__ __forceinline__ float rcp(float x) { float r; asm("rcp.approx.ftz.f32 %0, %1;" : "=f"(r) : "f"(x)); return r; }
__device__ __forceinline__ uint2 ld_relaxed2(const void* p) { uint2 v; asm volatile("ld.relaxed.gpu.global.v2.u32 {%0,%1}, [%2];" : "=r"(v.x), "=r"(v.y) : "l"(p) : "memory"); return v; }
__host__ __device__ constexpr uint64_t dconst(uint32_t lbo, uint32_t sbo, uint32_t swz) {
    return ((uint64_t)(lbo >> 4) << 16) | ((uint64_t)(sbo >> 4) << 32) | ((uint64_t)swz << 62);
}
__device__ __forceinline__ uint32_t mkdesc(uint32_t addr, uint64_t c) { return (uint32_t)c | ((addr & 0x3FFFF) >> 4); }
#define WG_FENCE() asm volatile("wgmma.fence.sync.aligned;" ::: "memory")
#define WG_COMMIT() asm volatile("wgmma.commit_group.sync.aligned;" ::: "memory")
#define WG_WAIT(n) asm volatile("wgmma.wait_group.sync.aligned %0;" ::"n"(n) : "memory")
template <int N> __device__ __forceinline__ void reg_fence(float* d) {
#pragma unroll
    for (int i = 0; i < N; i++) asm volatile("" : "+f"(d[i])::"memory");
}
template <int N> __device__ __forceinline__ void reg_def(float* d) {
#pragma unroll
    for (int i = 0; i < N; i++) asm volatile("" : "=f"(d[i]));
}
template <int N> __device__ __forceinline__ void reg_def(uint32_t* d) {
#pragma unroll
    for (int i = 0; i < N; i++) asm volatile("" : "=r"(d[i]));
}
__device__ __forceinline__ void wait_flags(const uint32_t* p, uint32_t target, uint32_t mask) {
    int n = 0;
    while (~__ballot_sync(~0u, ld_relaxed(p) == target) & mask) { if (++n > SPIN_LIMIT) __trap(); }
    asm volatile("fence.acquire.gpu;" ::: "memory");
}
__device__ __forceinline__ float silu_bf(uint32_t cbits) {
    const float c = __uint_as_float(cbits << 16);
    return bf_round(__fdividef(c, 1.f + fminf(ex2(-1.4426950408889634f * c), 1e30f)));
}
__device__ __forceinline__ void gemv_part(uint32_t wmbuf, int wp, int lane) {
    const uint32_t wa = wmbuf + wp * 512 + (8 * (lane >> 4) + (lane & 7)) * 32 + ((lane >> 3) & 1) * 16;
    float d[4] = {};
#pragma unroll
    for (int i = 0; i < 4; i++) {
        uint32_t A[4];
        const float2 v = lds2f(wmbuf + 28672 + (wp + 8 * i) * 32 + (lane & 3) * 8);
        ldsm4t(wa + (i < 3 || wp < 4 ? i : 0) * 4096, A);
        mma16816(d, A[0], A[1], A[2], A[3], __float_as_uint(v.x), __float_as_uint(v.y));
    }
    if ((lane & 3) == 0) {
        sts1(wmbuf + 29696 + (wp * 16 + (lane >> 2)) * 4, __float_as_uint(d[0]));
        sts1(wmbuf + 29696 + (wp * 16 + 8 + (lane >> 2)) * 4, __float_as_uint(d[2]));
    }
}
__device__ __forceinline__ uint32_t mod_word(float v, int col, uint32_t target) {
    v = bf_round(v);
    if ((col >= DM && col < 2 * DM) || (col >= 4 * DM && col < 5 * DM)) v += 1.f;
    return (pack2(v, 0.f) << 16) | (target & 0xFFFFu);
}
__device__ __forceinline__ const uint4* mod_src(int i, int r, int j, bool p2) {
    i = min(i, p2 ? 251 : 223);
    return (const uint4*)g_mod + (r & 7) * (6 * DM / 4) + (i < 224 ? (p2 ? 336 : 0) + i : (i < 238 ? 14 * j + i : 14 * j + i + 322));
}
__device__ __forceinline__ void mod_store(uint32_t sb, uint4 v, const uint4* src, int i) {
    const uint32_t tag = lds1(sb + M_EPOCH) + 1;
    while (__any_sync(~0u, (((v.x ^ tag) | (v.y ^ tag) | (v.z ^ tag) | (v.w ^ tag)) & 0xFFFFu) != 0u)) v = ld_relaxed4(src);
    if (i < 224) {
        const int isc = i >= 112, c4 = i - 112 * isc;
        const uint32_t a = sb + M_ST + (c4 >> 2) * 64 + (c4 & 1) * 32 + (c4 & 2) * 4 + (isc ? 0 : 4);
        sts1(a, __byte_perm(v.x, v.y, 0x7632));
        sts1(a + 16, __byte_perm(v.z, v.w, 0x7632));
    } else if (i < 252) {
        sts4(sb + M_G + (i - 224) * 16, make_uint4(v.x & 0xFFFF0000u, v.y & 0xFFFF0000u, v.z & 0xFFFF0000u, v.w & 0xFFFF0000u));
    }
}
__device__ __forceinline__ int pass_f(int fs, int ps) { return 224 * fs + ((fs & 1) ? (ps == 0 ? 96 : ps == 1 ? 32 : 0) : (ps == 0 ? 0 : ps == 1 ? 128 : 192)); }
__device__ __forceinline__ constexpr uint32_t slot_off(int l) { return l * 16384 + (l >= 10 ? 8192 : 0); }
constexpr uint64_t RING_ORDER = 0x6543C92B81A70ull;
constexpr uint32_t Y_XCH = 49152;
__device__ __forceinline__ constexpr int g1_slot(int s) { return s % 7; }
__device__ __noinline__ void x1_fix(const uint32_t* g, uint32_t sa, int s) {
#pragma unroll 1
    for (int k = 4 * s; k < 4 * s + 4;) {
        const uint4 v = ld_relaxed4((const uint4*)(g + k * 256));
        sts4(sa + k * 1024, v);
        k += 2 * __all_sync(~0u, min(min(v.x, v.y), min(v.z, v.w)) != 0u);
    }
    __syncwarp();
}
struct LnRow { uint32_t nm, hi, lo; };
__device__ __forceinline__ LnRow ln_coeffs(float mean, float msq) {
    const float var = bf_round(fmaxf(msq - mean * mean, 0.f));
    float sd;
    asm("sqrt.approx.f32 %0, %1;" : "=f"(sd) : "f"(bf_round(var + 1e-5f)));
    const float inv = rcp(bf_round(sd)), hi = bf_round(inv);
    LnRow c;
    c.nm = pack2(-bf_round(mean) * hi, -bf_round(mean) * hi);
    c.hi = pack2(hi, hi);
    c.lo = pack2(inv - hi, inv - hi);
    return c;
}
__device__ __forceinline__ uint32_t ln_norm(uint32_t x, const LnRow& c) {
    return hfma2(x, c.hi, c.nm);
}
__device__ __forceinline__ uint32_t ln_mod(uint32_t y, uint32_t sc, uint32_t sh) {
    return hfma2(y, sc, sh);
}

#define LOADW bulk_e(dst, g_wd + (size_t)((f >> 5) * 4 + nq) * 1792, 7168, bar);
template <int sec> __device__ __forceinline__ void ring_loader(const Params& p, uint32_t sb_, int r_, int j_, int lane) {
    const uint32_t sb = opaque(sb_);
    const int r = opaque(r_), j = opaque(j_), nq = j >> 1, fs = 4 * (j & 1) + nq;
    const int fa = pass_f(fs, 0), fb = pass_f(fs, 1), fc = pass_f(fs, 2);
    const uint32_t* h2src = (const uint32_t*)__shfl_sync(~0u, (unsigned long long)(p.actb + (size_t)r * RB_WORDS + RB_H2), 0);
    const CUtensorMap* gmap = (const CUtensorMap*)__shfl_sync(~0u, (unsigned long long)(&p.ga + sec), 0);
#define BAR(i) (sb + M_BAR + 8 * (i))
#define kh (j & 1)
            int sl = 0;
#pragma unroll 1
            for (int s = 0; s < 21; s++) {
                if (s == 7) { wait_flags(g_flag + (8 * r + j) * 192 + 96 + lane, lds1(sb + M_EPOCH) + 1, 0xFFFFu); fence_async_global(); }
                if (s >= 1 && s < 6) mbar_wait(BAR(B_FULL + s - 1), 0);
                mbar_wait(BAR(B_EMPTY + sl), s >= 7 && s < 14);
                expect_e(BAR(B_FULL + sl), 8192);
                tma3_e(sb + slot_off(sl) + sec * 8192, gmap + (s < 14 ? 0 : 2), 0, s < 14 ? 32 * s : 64 * sl, (s < 14 ? fa : fb) >> 6, BAR(B_FULL + sl));
                sl = sl == 6 ? 0 : sl + 1;
            }
#pragma unroll 1
            for (int s = 0; s < 7; s++) {
                const uint32_t bar = BAR(B_FULL + s);
                uint32_t dst = sb + slot_off(s) + sec * 4096;
                mbar_wait(BAR(B_EMPTY + s), 1);
                expect_e(bar, s < 3 ? 8192 : s > 3 ? 7168 : sec ? 4096 : 4096 + 7168);
                if (s < 4) tma3_e(dst, gmap + 4, 0, 128 * s, fc >> 5, bar);
                if (s < 3) tma3_e(dst + 8192, gmap + 4, 0, 128 * s + 64, fc >> 5, bar);
                else if (s > 3 || !sec) {
                    const int f = s == 3 ? fc : (s < 6 ? fa + 64 * (s - 4) : fb) + 32 * sec;
                    dst = sb + slot_off(s) + (s == 3 || sec ? 8192 : 0);
                    LOADW
                }
            }
            if (!sec) PROFH(3);
            if (sec) asm volatile("prefetch.tensormap [%0];" ::"l"(&p.om) : "memory");
            int e = 0;
#pragma unroll 1
            for (int grp = 0; grp < 9; grp++) {
                const int ps = grp >= 6 ? 2 : grp >= 3 ? 1 : 0;
                int sidx = grp - 3 * ps;
                if (sec && sidx == 0) { mbar_wait(BAR(B_HRDY + ps), 0); fence_async_global(); }
                sidx += sidx >= nq;
                int f = pass_f(4 * kh + sidx, ps);
#pragma unroll 1
                for (int k = 4 >> ps; k > 0; k--, e++, f += 32) {
                    sl = (RING_ORDER >> (4 * (e < 13 ? e : e - 13))) & 15;
                    const uint32_t dst = sb + slot_off(sl), bar = BAR(B_FULL + sl);
                    mbar_wait(BAR(B_EMPTY + sl), e >= 13);
                    if (e >= WIN) mbar_wait(BAR(B_FULL + ((RING_ORDER >> (4 * (e - WIN < 13 ? e - WIN : e - WIN - 13))) & 15)), e - WIN >= 13);
                    expect_e(bar, sec ? 8192 : 7168);
                    if (!sec) { LOADW }
                    else bulk_e(dst + 8192, h2src + f * 64, 8192, bar);
                }
            }
            if (!sec) PROFH(4);
}

#define PROF_PARAMS
#define PROF_ARGS
__device__ __noinline__ void helper_late(const Params& p, int r_, int j_, int warp_ PROF_PARAMS) {
    extern __shared__ __align__(1024) unsigned char smem[];
    const uint32_t sb = (uint32_t)__cvta_generic_to_shared(smem);
    const int r = opaque(r_), j = opaque(j_), warp = opaque(warp_), nq = j >> 1, b = 8 * r + j;
    uint32_t* const act = (uint32_t*)__shfl_sync(~0u, (unsigned long long)(p.actb + (size_t)r * RB_WORDS), 0);
    {
        const int lane = fresh_tid() & 31;
        const uint32_t target = lds1(sb + M_EPOCH) + 1;
        if (warp == 8) { expect_e(BAR(B_XCH), 7168); expect_e(BAR(B_XCH + 1), 7168); }
            if (warp == 9) {
#pragma unroll 1
                for (int kv = 0; kv < 2; kv++) {
                    mbar_wait(BAR(B_PUB + kv), 0);
                    wait_flags(g_flag + b * 192 + lane, target, (r >= 2 ? 6u : r == 1 ? 2u : 0u) << (8 * kv));
                    fence_async_global();
                    const uint32_t dst = sb + OFF_Y + (kv ? Y_VR : Y_K);
                    expect_e(BAR(B_KRFULL + kv), r >= 2 ? 28672 : r == 1 ? 14336 : 0);
                    if (r >= 2) bulk_e(dst, act - 2 * RB_WORDS + RB_KV + j * 7168 + kv * 3584, 14336, BAR(B_KRFULL + kv));
                    if (r >= 1) bulk_e(dst + 14336, act - RB_WORDS + RB_KV + j * 7168 + kv * 3584, 14336, BAR(B_KRFULL + kv));
                    if (kv == 0) { PROFH(8); }
                }
            } else if (warp == 8) {
                uint4 v[8];
                mbar_wait(BAR(B_WOFULL), 0);
#pragma unroll
                for (int k = 0; k < 8; k++) v[k] = ld_relaxed4(mod_src(lane + 32 * k, r, j, true));
#pragma unroll
                for (int k = 0; k < 8; k++) mod_store(sb, v[k], mod_src(lane + 32 * k, r, j, true), lane + 32 * k);
                warp_arrive(BAR(B_MOD1));
            } else if (warp == 11) {
                if (kh == 1 && r < 14) {
                    const uint32_t wmbuf = sb + OFF_X + HALF;
                    const int mcol = 2 * DM + 32 * (4 * r + nq);
                    mbar_wait(BAR(B_XFREE), 0);
                    tma3_e(wmbuf, &p.wm2, mcol, 0, 0, BAR(B_WMFULL));
                    tma3_e(wmbuf + 14336, &p.wm2, mcol, 224, 0, BAR(B_WMFULL));
#pragma unroll 1
                    for (int wd = lane; wd < 224; wd += 32) {
                        const uint32_t cb = __ldg((const uint32_t*)p.c + wd);
                        sts1(wmbuf + 28672 + (wd >> 3) * 32 + (wd & 3) * 8 + (wd & 4), pack2(silu_bf(cb & 0xFFFFu), silu_bf(cb >> 16)));
                    }
                    __syncwarp();
                    mbar_wait(BAR(B_WMFULL), 0);
                    const uint32_t wa = wmbuf + (8 * (lane >> 4) + (lane & 7)) * 64 + ((lane >> 3) & 1) * 16;
                    float d[2][4] = {};
#pragma unroll 4
                    for (int ks = 0; ks < 28; ks++) {
                        uint32_t A[8];
                        ldsm4t(wa + ks * 1024, A); ldsm4t(wa + ks * 1024 + 32, A + 4);
                        const float2 v = lds2f(wmbuf + 28672 + ks * 32 + (lane & 3) * 8);
                        mma16816(d[0], A[0], A[1], A[2], A[3], __float_as_uint(v.x), __float_as_uint(v.y));
                        mma16816(d[1], A[4], A[5], A[6], A[7], __float_as_uint(v.x), __float_as_uint(v.y));
                    }
                    const int q = lane & 3, col = mcol + 8 * q + (lane >> 2);
                    const uint32_t word = mod_word(q == 0 ? d[0][0] : q == 1 ? d[0][2] : q == 2 ? d[1][0] : d[1][2], col, target);
#pragma unroll
                    for (int i = 0; i < 8; i++) st_relaxed(g_mod + i * 6 * DM + col, word);
                }
                warp_arrive(BAR(B_WMFREE));
                mbar_wait(BAR(B_VRFULL), 0);
                l2_prefetch_e((const char*)p.wg + (size_t)b * 12544, 12544);
                l2_prefetch_e((const char*)p.wu + (size_t)b * 12544, 12544);
#pragma unroll 1
                for (int k = 0; k < (r < 12 ? 2 : 1); k++) {
                    const int u = 28 * kh + r + 16 * k;
                    expect_e(BAR(B_XFULL + k), 7168);
                    tma3_e(sb + OFF_Y + 102400, &p.dn, 0, 32 * u, 7 * j, BAR(B_XFULL + k));
                    tma3_e(sb + OFF_Y + 102400 + 3584, &p.dn, 0, 32 * u, 7 * (j ^ 1), BAR(B_XFULL + k));
                    mbar_wait(BAR(B_XFULL + k), 1);
                    asm volatile("{\n.reg .pred p;\nelect.sync _|p, 0xffffffff;\n@p cp.async.bulk.global.shared::cta.bulk_group [%0], [%1], 7168;\n"
                                 "cp.async.bulk.commit_group;\ncp.async.bulk.wait_group 0;\n}" ::"l"(g_wd + (size_t)(u * 4 + nq) * 1792), "r"(sb + OFF_Y + 102400) : "memory");
                    __syncwarp();
                }
                warp_arrive(BAR(B_FULLK));
                fence_gpu();
                if (lane < 16) st_relaxed(g_flag + (8 * lane + j) * 192 + 96 + r, target);
            }
        if (warp == 8 || warp == 11) {
            const int sec = warp == 11;
            if (sec) ring_loader<1>(p, sb, r, j, lane); else ring_loader<0>(p, sb, r, j, lane);
            mbar_wait(BAR(B_DONE), 0);
        } else if (warp == 9) {
#pragma unroll
            for (int ev = 0; ev < 4; ev++) { expect_e(BAR(B_GFULL + ev), ev < 2 ? HALF / 2 : 16384); expect_e(BAR(B_XFULL + 2 + ev), ev < 2 ? HALF / 2 : HALF - 16384); }
            mbar_wait(BAR(B_PUB + 2), 0);
            expect_e(BAR(B_FULLV), 4096); expect_e(BAR(B_FULLQ), 4096);
            const int par = (target - 1) & 1;
#pragma unroll 1
            for (int ev = 0; ev < 4; ev++) {
                if (ev == 1) { mbar_wait(BAR(B_FULLK), 1); mbar_wait(BAR(B_PUB + 3), 0); }
                const int tile = (ev & 1) + (ev >> 1) * par * 2;
                const uint32_t dst = sb + (ev == 0 ? OFF_X : OFF_Y + (ev & 1) * HALF), first = ev < 2 ? HALF / 2 : 16384;
                const char* src = (const char*)(act + RB_O + ((ev >> 1) * 2 + tile) * 14336);
                wait_flags(g_flag + b * 192 + (ev < 2 ? 32 : 64 + 32 * ev) + lane, target, ev < 2 ? 0xFFu << (8 * ev) : ~0u);
                fence_async_global();
                if (ev >= 2) bulk_e(sb + OFF_X + X_STAT + (ev & 1) * 49152, act + RB_ST + tile * 1024, 4096, BAR(B_FULLV + (ev & 1)));
                bulk_e(dst, src, first, BAR(B_GFULL + ev));
                bulk_e(dst + first, src + first, HALF - first, BAR(B_XFULL + 2 + ev));
                if (ev) PROFH(4 + ev);
            }
            mbar_wait(BAR(B_XFULL + 5), 1);
#pragma unroll 1
            for (int hf = 0; hf < 2; hf++) {
                const int tile = (par ^ 1) * 2 + hf;
                uint4* xz = (uint4*)(act + RB_X1 + tile * 14336 + j * 1792) + lane;
#pragma unroll
                for (int i = 0; i < 14; i++) xz[i * 32] = make_uint4(0, 0, 0, 0);
                ((uint4*)(act + RB_ST + (tile * 8 + j) * 128))[lane] = make_uint4(0, 0, 0, 0);
            }
#pragma unroll 1
            for (int ps = 0; ps < 3; ps++) {
                mbar_wait(BAR(B_PUB + 6 + ps), 0);
                if (ps == 1) {
                    fence_gpu();
                    if (lane < 8) st_relaxed(g_flag + (8 * r + lane) * 192 + 72 + j, target);
                }
                wait_flags(g_flag + b * 192 + 64 + lane, target, (0x55u << kh) << (8 * ps));
                warp_arrive(BAR(B_HRDY + ps));
                PROFH(9 + ps);
            }
        } else {
#pragma unroll 1
            for (int k = 0; k < 9; k++) {
                if (k == 4 || k == 5 || k == 7) continue;
                uint32_t* fp = k < 2 ? g_flag + (b + 8 * lane) * 192 + k * 8 + lane : g_flag + (8 * r + lane) * 192 + 16 + k * 8 + j;
                mbar_wait(BAR(B_PUB + k), 0);
                fence_gpu();
                if (k < 2 ? (lane == 1 || lane == 2) : lane < 8) st_relaxed(fp, target);
                if (k >= 3 && k <= 5) PROFH(k - 3);
            }
        }
    }
}

__global__ void __cluster_dims__(2, 1, 1) __launch_bounds__(384, 1) fused_block_kernel(const __grid_constant__ Params p) {
    extern __shared__ __align__(1024) unsigned char smem[];
    const uint32_t sb = (uint32_t)__cvta_generic_to_shared(smem);
    const int tid = threadIdx.x, lane = tid & 31, warp = __shfl_sync(~0u, tid >> 5, 0);
    const int m = blockIdx.x >> 1;
    int r, nq;
    if (m < 4) { r = 15; nq = m; }
    else if (m < 36) { r = (m - 4) & 7; nq = (m - 4) >> 3; }
    else { nq = (m - 36) / 7; r = m - 28 - 7 * nq; }
    const int j = opaque(2 * nq + (blockIdx.x & 1)), b = 8 * r + j, fs = 4 * kh + nq;
#define act (p.actb + (size_t)r * RB_WORDS)
    uint32_t ticket = 0;
    if (tid == 288) ticket = atomicAdd(&g_ticket, 1u);
    if (warp == 10 && blockIdx.x < 112) {
#pragma unroll
        for (int i = 0; i < 4; i++) l2_prefetch_e(p.wmod + (size_t)(4 * blockIdx.x + i) * (6 * DM), 4 * DM);
    }
    if (warp == 11) l2_prefetch_e((const char*)p.x + (size_t)blockIdx.x * 14336, 14336);
    if (lane == 0 && warp < 9 && warp != 6 && warp != 7) {
        const int i0 = warp == 8 ? 0 : 8 + 8 * warp, cnt = warp == 0 || warp == 8 ? 1 : warp < 3 ? 2 : 8;
#pragma unroll
        for (int k = 0; k < 8; k++) if (i0 + k != B_WMFULL) mbar_init(BAR(i0 + k), cnt);
        if (warp == 8) mbar_init(BAR(B_WMFULL), 1);
        asm volatile("fence.mbarrier_init.release.cluster;" ::: "memory");
        fence_async_smem();
    }

    if (warp >= 8) {
        const int lane = fresh_tid() & 31;
        const bool early = kh == 0, gemv = r < 14;
        const int mcol = early ? 16 * (4 * r + nq) : 2 * DM + 32 * (4 * r + nq);
        const uint32_t wmbuf = sb + OFF_Y + HALF;
        if (warp == 8) {
            __syncwarp();
            expect_e(BAR(B_WMFULL), gemv ? 28672 >> early : 0);
            if (early && gemv) { tma3_e(wmbuf, &p.wm, mcol, 0, 0, BAR(B_WMFULL)); tma3_e(wmbuf + 7168, &p.wm, mcol, 224, 0, BAR(B_WMFULL)); }
#pragma unroll
            for (int kb = 0; kb < 7; kb++) {
                expect_e(BAR(B_XFULL + kb), 16384);
                tma3_e(sb + OFF_X + kb * 16384, &p.xm, 64 * kb, 128 * r, 0, BAR(B_XFULL + kb));
            }
        }
        asm volatile("setmaxnreg.dec.sync.aligned.u32 56;");
        if (warp == 10) {
#pragma unroll
            for (int i = 56; i < 64; i++) init_e(BAR(i), 1);
            fence_async_smem();
        }
        bar_arrive(0, 384);
        asm volatile("barrier.cluster.arrive.relaxed.aligned;" ::: "memory");
        if (warp == 8) {
            mbar_wait(BAR(B_XFULL), 0);
            l2_prefetch_e((const char*)p.wqkv + (size_t)b * 9408, 9408);
#pragma unroll 1
            for (int mt = 0; mt < 4; mt++) {
                if (mt == 1) bar_sync(9, 384);
                if (mt == 3) mbar_wait(BAR(B_WMFREE), 0);
                if (mt == 1 && early) mbar_wait(BAR(B_WMFREE), 0);
                if (mt) mbar_wait(BAR(mt == 1 ? B_FULLK : mt == 2 ? B_MOD1 : B_VRFULL), 0);
                const uint32_t bar = BAR(mt == 3 ? B_WOFULL : B_FULLK + mt), dst = sb + (mt < 2 ? OFF_Y : OFF_X) + (mt & 1) * HALF;
                const int c0 = (mt < 2 ? DM + DM * mt : 0) + 56 * j - 8 * kh;
                expect_e(bar, HALF);
                tma3_e(dst, mt == 3 ? &p.wo : &p.qkv, c0, 0, 0, bar);
                tma3_e(dst + HALF / 2, mt == 3 ? &p.wo : &p.qkv, c0, 224, 0, bar);
            }
        } else {
            if (warp == 10 && lane < 13) asm volatile("prefetch.tensormap [%0];" ::"l"(&p.wm + lane) : "memory");
            if (tid == 288) sts1(sb + M_EPOCH, ticket / NCTA);
            bar_sync(9, 384);
            if (warp == 9 && lane < 8) mbar_arrive(BAR(B_EPOCH));
            if (warp == 11 && early) {
                const uint32_t target = lds1(sb + M_EPOCH) + 1;
                mbar_wait(BAR(B_GEMV), 0);
                float sum = 0.f;
#pragma unroll
                for (int i = 0; i < 8; i++) sum += *(const float*)(smem + OFF_Y + HALF + 29696 + (i * 16 + (lane & 15)) * 4);
                uint32_t* mg = g_mod + mcol + (lane & 15) + (lane >> 4) * 4 * 6 * DM;
                const uint32_t word = mod_word(sum, mcol, target);
                if (gemv) { st_relaxed(mg, word); st_relaxed(mg + 6 * DM, word); st_relaxed(mg + 12 * DM, word); st_relaxed(mg + 18 * DM, word); }
            }
        }
    }
    if (warp < 8) {
        const int w = (warp >> 2) ^ 1, wi = warp & 3;
#define COORDS const int t = fresh_tid() & 127, lane = t & 31, q = lane & 3, lr = lane >> 2, ra = 64 * w + 16 * wi + lr; \
        const uint32_t lx = (lane >> 4) ^ (lane & 7), mrow = (64 * w + 16 * wi + ((lane >> 3) & 1) * 8 + (lane & 7)) * 128; \
        (void)q; (void)lr; (void)ra; (void)lx; (void)mrow;
#define WAIT(i, par) mbar_wait_c(BAR(i), par)
        constexpr uint64_t DB128 = dconst(4096, 1024, 1);
        {
            const int wd = fresh_tid();
            const uint32_t cb = wd < 224 ? __ldg((const uint32_t*)p.c + wd) : 0u;
            sts1(sb + OFF_Y + HALF + 28672 + (wd >> 3) * 32 + (wd & 3) * 8 + (wd & 4), pack2(silu_bf(cb & 0xFFFFu), silu_bf(cb >> 16)));
        }
        bar_arrive(9, 384);
        bar_sync(0, 384);
        asm volatile("barrier.cluster.arrive.relaxed.aligned;" ::: "memory");
        asm volatile("setmaxnreg.inc.sync.aligned.u32 224;");
        PROFC(0);
        uint32_t xr[16];
        {
            COORDS
            uint32_t h[112];
            LnRow ca, cb;
            const int mi = min(128 * w + t, 223);
            const uint4* msrc = mod_src(mi, r, j, false);
            uint4 mv;
            {
                float ds[4] = {}, da[2][4] = {}, db[2][4] = {};
                const uint32_t ONE2 = 0x3F803F80u;
#pragma unroll
                for (int kb = 0; kb < 7; kb++) {
                    if (kb == 0 && kh == 0) { WAIT(B_WMFULL, 0); gemv_part(sb + OFF_Y + HALF, warp, lane); warp_arrive(BAR(B_GEMV)); }
                    WAIT(B_XFULL + kb, 0);
#pragma unroll
                    for (int k4 = 0; k4 < 4; k4++) ldsm4(sb + OFF_X + mrow + kb * 16384 + (((2 * k4) ^ lx) << 4), h + 16 * kb + 4 * k4);
#pragma unroll
                    for (int k4 = 0; k4 < 4; k4++) {
                        const uint32_t* f = h + 16 * kb + 4 * k4;
                        mma16816(ds, f[0], f[1], f[2], f[3], ONE2, ONE2);
                        mma1688(da[0], f[0], f[1], f[0]); mma1688(db[0], f[0], f[1], f[1]);
                        mma1688(da[1], f[2], f[3], f[2]); mma1688(db[1], f[2], f[3], f[3]);
                    }
                }
#pragma unroll
                for (int i = 0; i < 4; i++) {
                    const int ch = 7 * j + 2 * i + (lane >> 4);
                    ldsm4(sb + OFF_X + mrow + (ch >> 3) * 16384 + (((ch ^ lane) & 7) << 4), xr + 4 * i);
                }
                mv = ld_relaxed4(msrc);
                warp_arrive(BAR(B_XFREE));
                float qa = (lr & 1) ? da[0][1] + da[1][1] : da[0][0] + da[1][0];
                float qb = (lr & 1) ? db[0][3] + db[1][3] : db[0][2] + db[1][2];
                const int src = (lane & ~3) | (lr >> 1);
                qa = __shfl_sync(~0u, qa, src);
                qb = __shfl_sync(~0u, qb, src);
                ca = ln_coeffs(ds[0] * (1.f / DM), qa * (1.f / DM));
                cb = ln_coeffs(ds[2] * (1.f / DM), qb * (1.f / DM));
#pragma unroll
                for (int i = 0; i < 4 * NPRE; i += 2) { h[i] = ln_norm(h[i], ca); h[i + 1] = ln_norm(h[i + 1], cb); }
            }
            PROFC(1);
            {
                float ak[28], av[28], aq[28];
                uint32_t kp[14], vp[14];
                const uint64_t bq0 = (DB128 & ~0xFFFFFFFFull) | (mkdesc(sb + OFF_X, DB128) + kh), bk0 = bq0 + (OFF_Y >> 4), bv0 = bk0 + (HALF >> 4);
                uint32_t* kvg = act + RB_KV + j * 7168 + (8 * w + 2 * wi) * 224 + lane;
                WAIT(B_EPOCH, 0);
                mod_store(sb, mv, msrc, mi);
                bar_sync(3, 256);
                if (warp == 0) warp_arrive(BAR(B_MOD1));
                WAIT(B_FULLK, 0);
                PROFC(2);
                reg_def<28>(ak);
#pragma unroll
                for (int g4 = 0; g4 < 4; g4++) {
#pragma unroll
                    for (int ks = 7 * g4; ks < 7 * g4 + 7; ks++) {
                        const uint4 st = *(const uint4*)(smem + M_ST + ks * 64 + q * 16);
                        if (ks >= NPRE) {
                            h[4 * ks] = ln_norm(h[4 * ks], ca); h[4 * ks + 1] = ln_norm(h[4 * ks + 1], cb);
                            h[4 * ks + 2] = ln_norm(h[4 * ks + 2], ca); h[4 * ks + 3] = ln_norm(h[4 * ks + 3], cb);
                        }
                        h[4 * ks] = ln_mod(h[4 * ks], st.x, st.y); h[4 * ks + 1] = ln_mod(h[4 * ks + 1], st.x, st.y);
                        h[4 * ks + 2] = ln_mod(h[4 * ks + 2], st.z, st.w); h[4 * ks + 3] = ln_mod(h[4 * ks + 3], st.z, st.w);
                    }
                    WG_FENCE();
#pragma unroll
                    for (int ks = 7 * g4; ks < 7 * g4 + 7; ks++) wgmma_rl_56(ak, h[4 * ks], h[4 * ks + 1], h[4 * ks + 2], h[4 * ks + 3], bk0 + ks * 128, ks != 0);
                }
                WG_COMMIT();
                PROFC(3);
                reg_def<28>(av);
                WG_WAIT(0);
                reg_fence<28>(ak);
#pragma unroll
                for (int g = 0; g < 7; g++) {
                    kp[2 * g] = pack2(ak[4 * g], ak[4 * g + 1]); kp[2 * g + 1] = pack2(ak[4 * g + 2], ak[4 * g + 3]);
                    kvg[g * 32] = kp[2 * g]; kvg[224 + g * 32] = kp[2 * g + 1];
                }
                warp_arrive(BAR(B_PUB));
                PROFC(4);
                WAIT(B_FULLV, 0);
                WG_FENCE();
#pragma unroll
                for (int ks = 0; ks < 28; ks++) wgmma_rl_56(av, h[4 * ks], h[4 * ks + 1], h[4 * ks + 2], h[4 * ks + 3], bv0 + ks * 128, ks != 0);
                WG_COMMIT();
                reg_def<28>(aq);
                WAIT(B_FULLQ, 0);
                WG_FENCE();
#pragma unroll
                for (int ks = 0; ks < VPRE; ks++) wgmma_rl_56(aq, h[4 * ks], h[4 * ks + 1], h[4 * ks + 2], h[4 * ks + 3], bq0 + ks * 128, ks != 0);
                WG_COMMIT();
                WG_WAIT(1);
                reg_fence<28>(av);
#pragma unroll
                for (int g = 0; g < 7; g++) {
                    vp[2 * g] = pack2(av[4 * g], av[4 * g + 1]); vp[2 * g + 1] = pack2(av[4 * g + 2], av[4 * g + 3]);
                    kvg[3584 + g * 32] = vp[2 * g]; kvg[3584 + 224 + g * 32] = vp[2 * g + 1];
                }
                warp_arrive(BAR(B_PUB + 1));
                PROFC(5);
                WG_FENCE();
#pragma unroll
                for (int ks = VPRE; ks < 28; ks++) wgmma_rl_56(aq, h[4 * ks], h[4 * ks + 1], h[4 * ks + 2], h[4 * ks + 3], bq0 + ks * 128, ks != 0);
                WG_COMMIT();
                WAIT(B_PUB + 1, 0);
                const uint32_t rg = 8 * w + 2 * wi + ((lane >> 3) & 1);
                const uint32_t ko = sb + OFF_Y + Y_KOWN + rg * 896 + (lane & 7) * 16, qo = sb + OFF_Y + Y_Q + rg * 1024 + (lane >> 4) * 128 + (lane & 7) * 16;
#pragma unroll
                for (int g = 0; g < 6; g += 2) {
                    stsm4(ko + (g + (lane >> 4)) * 128, kp[2 * g], kp[2 * g + 1], kp[2 * g + 2], kp[2 * g + 3]);
                    stsm4(ko + (Y_VOWN - Y_KOWN) + (g + (lane >> 4)) * 128, vp[2 * g], vp[2 * g + 1], vp[2 * g + 2], vp[2 * g + 3]);
                }
                stsm4(ko + (lane >> 4) * (Y_VOWN - Y_KOWN) + 6 * 128, kp[12], kp[13], vp[12], vp[13]);
                WG_WAIT(0);
                reg_fence<28>(aq);
                __syncwarp();
                if (lane < 3 && w == 1) mbar_arrive(BAR(B_EMPTY + lane));
                uint32_t qp[14];
#pragma unroll
                for (int i = 0; i < 14; i++) qp[i] = pack2(aq[2 * i], aq[2 * i + 1]);
                stsm4(qo, qp[0], qp[1], qp[2], qp[3]);
                stsm4(qo + 256, qp[4], qp[5], q < 2 ? qp[6] : 0u, q < 2 ? qp[7] : 0u);
                stsm4(qo + 512, q < 2 ? 0u : qp[6], q < 2 ? 0u : qp[7], qp[8], qp[9]);
                stsm4(qo + 768, qp[10], qp[11], qp[12], qp[13]);
                fence_async_smem();
                if (w == 0) { bar_arrive(4, 256); bar_sync(1, 128); } else { bar_arrive(5, 256); bar_sync(4, 256); }
            }
        }
        PROFC(6);
        WAIT(B_KRFULL, 0);
        PROFC(7);
        {
#pragma unroll 1
            for (int hf = 0; hf < 2; hf++) {
                COORDS
                if (hf > w) bar_sync(5, 256);
                float s[160];
                const float CS = 0.18898223650461361f * 1.4426950408889634f;
                const float NEG = __int_as_float(0xFF800000);
                constexpr uint64_t DQ = dconst(128, 1024, 0), DK = dconst(128, 896, 0);
                {
                    const uint32_t qd = mkdesc(sb + OFF_Y + Y_Q + hf * 8192 + w * 512, DQ), kd = mkdesc(sb + OFF_Y + Y_K + hf * 8 * 896 + w * 384, DK);
                    reg_def<160>(s);
                    WG_FENCE();
                    wgmma_sk_160<DQ, DK>(s, qd, kd, 0);
                    wgmma_sk_160<DQ, DK>(s, qd + 16, kd + 16, 1);
                    WG_COMMIT();
                    wgmma_sk_160<DQ, DK>(s + 80, qd, kd + 20 * 56, 0);
                    wgmma_sk_160<DQ, DK>(s + 80, qd + 16, kd + 20 * 56 + 16, 1);
                    WG_COMMIT();
                }
                const int pmin = 8 - 4 * r - 2 * hf;
                const bool c0 = 2 * q > lr, c1 = 2 * q + 1 > lr;
                int i0 = 0x80000000, i1 = 0x80000000, i2 = 0x80000000, i3 = 0x80000000;
#pragma unroll
                for (int hh = 0; hh < 2; hh++) {
                    if (hh == 0) WG_WAIT(1); else WG_WAIT(0);
                    reg_fence<80>(s + 80 * hh);
                    if (r < 2) {
#pragma unroll
                        for (int p2 = 5 * hh; p2 < (hh ? 8 : 5); p2++)
                            if (p2 < pmin) {
#pragma unroll
                                for (int i = 0; i < 16; i++) asm volatile("mov.b32 %0, 0xFF800000;" : "=f"(s[16 * p2 + i]));
                            }
                    }
#pragma unroll
                    for (int pp = 0; pp < 4; pp++) {
                        const bool me = pp == wi;
                        float* e = s + 8 * (pp + 16 * hh);
                        if (me && c0 == hh) { e[0] = NEG; e[6] = NEG; }
                        if (me && c1 == hh) { e[1] = NEG; e[7] = NEG; }
                        if (me) { e[2 + 2 * hh] = NEG; e[3 + 2 * hh] = NEG; }
                    }
                    if (hh) {
#pragma unroll
                        for (int i = 0; i < 24; i++) s[i] = (i >> 3) < wi ? s[136 + i] : s[i];
                    }
#pragma unroll
                    for (int pp = 0; pp < 17; pp++) {
                        if ((pp >= 3 && pp < 10) == (hh == 0)) {
                            const float* e = s + 8 * pp;
                            i0 = __vimax3_s32(i0, __float_as_int(e[0]), __float_as_int(e[1])); i1 = __vimax3_s32(i1, __float_as_int(e[2]), __float_as_int(e[3]));
                            i2 = __vimax3_s32(i2, __float_as_int(e[4]), __float_as_int(e[5])); i3 = __vimax3_s32(i3, __float_as_int(e[6]), __float_as_int(e[7]));
                        }
                    }
                }
                i0 = max(i0, i2); i1 = max(i1, i3);
                i0 = max(i0, __shfl_xor_sync(~0u, i0, 1)); i1 = max(i1, __shfl_xor_sync(~0u, i1, 1));
                i0 = max(i0, __shfl_xor_sync(~0u, i0, 2)); i1 = max(i1, __shfl_xor_sync(~0u, i1, 2));
                if (__any_sync(~0u, (i0 | i1) < 0)) {
                    uint32_t u0 = ~0u, u1 = ~0u, u2 = ~0u, u3 = ~0u;
#pragma unroll
                    for (int pp = 0; pp < 17; pp++) {
                        const float* e = s + 8 * pp;
                        u0 = __vimin3_u32(u0, __float_as_uint(e[0]), __float_as_uint(e[1])); u1 = __vimin3_u32(u1, __float_as_uint(e[2]), __float_as_uint(e[3]));
                        u2 = __vimin3_u32(u2, __float_as_uint(e[4]), __float_as_uint(e[5])); u3 = __vimin3_u32(u3, __float_as_uint(e[6]), __float_as_uint(e[7]));
                    }
                    u0 = min(u0, u2); u1 = min(u1, u3);
                    u0 = min(u0, __shfl_xor_sync(~0u, u0, 1)); u1 = min(u1, __shfl_xor_sync(~0u, u1, 1));
                    u0 = min(u0, __shfl_xor_sync(~0u, u0, 2)); u1 = min(u1, __shfl_xor_sync(~0u, u1, 2));
                    if (i0 < 0) i0 = u0;
                    if (i1 < 0) i1 = u1;
                }
                const float ma = __int_as_float(i0), mb = __int_as_float(i1);
                const float na = -ma * CS, nb = -mb * CS;
                PROFC(8 + 3 * hf);
                {
                    WAIT(B_VRFULL, 0);
                    float o[16] = {}, rs[4] = {};
                    const uint32_t va = sb + OFF_Y + Y_VR + (8 * hf + ((lane >> 3) & 1)) * 896 + (3 * w + (lane >> 4)) * 128 + (lane & 7) * 16;
                    constexpr uint32_t OWN = Y_VOWN - 32 * 896;
#pragma unroll
                    for (int pp = 0; pp < 17; pp++) {
                        uint32_t B[8];
                        const uint32_t v = va + pp * 1792 + (pp < 3 ? (pp < wi ? 17 * 1792 + OWN : 0) : pp == 16 ? OWN : pp >= 12 ? hf * OWN : 0);
                        ldsm4t(v, B); ldsm4t(v + 256, B + 4);
                        float e[8];
#pragma unroll
                        for (int i = 0; i < 8; i++) e[i] = ex2(fmaf(s[8 * pp + i], CS, (i & 2) ? nb : na));
                        const uint32_t p0 = pack2(e[0], e[1]), p1 = pack2(e[2], e[3]), p2 = pack2(e[4], e[5]), p3 = pack2(e[6], e[7]);
                        mma16816(rs, p0, p1, p2, p3, 0x3F803F80u, 0x3F803F80u);
#pragma unroll
                        for (int g = 0; g < 4; g++) mma16816(o + 4 * g, p0, p1, p2, p3, B[2 * g], B[2 * g + 1]);
                    }
                    PROFC(9 + 3 * hf);
                    const float ia = rcp(rs[0]), ib = rcp(rs[2]);
                    uint32_t* og = act + RB_O + hf * 14336 + (7 * j + 3 * w) * 256 + wi * 64 + lane;
#pragma unroll
                    for (int g = 0; g < 4; g++) {
                        if ((g == 3 - 3 * w) ? ((q >> 1) == w) : true) {
                            og[g * 256] = pack2(o[4 * g] * ia, o[4 * g + 1] * ia);
                            og[g * 256 + 32] = pack2(o[4 * g + 2] * ib, o[4 * g + 3] * ib);
                        }
                    }
                    warp_arrive(BAR(B_PUB + 2 + hf));
                    PROFC(10 + 3 * hf);
                }
            }
        }
        uint32_t x1p[14];
        COORDS
        constexpr uint64_t DT = dconst(1024, 128, 0);
        const uint32_t epoch = lds1(sb + M_EPOCH);
        const int tile = opaque((epoch & 1) * 2 + w);
        {
            float ac[28];
            const uint32_t ad = mkdesc(sb + (w ? OFF_Y + HALF : OFF_X), DT), bd = mkdesc(sb + OFF_X + HALF, DB128) + kh;
            WAIT(B_WOFULL, 0);
            WAIT(B_MOD1, 1);
            WAIT(B_GFULL + w, 0);
            PROFC(28);
            reg_def<28>(ac);
#pragma unroll 1
            for (int u = 0; u < 4; u++) {
                if (u == 2) WAIT(B_XFULL + 2 + w, 1);
                WG_FENCE();
#pragma unroll
                for (int i = 0; i < 7; i++) wgmma_ss_56<DT, DB128>(ac, ad + (7 * u + i) * 128, bd + (7 * u + i) * 128, (u | i) != 0);
            }
            WG_COMMIT();
            WG_WAIT(0);
            reg_fence<28>(ac);
            PROFC(14);
            __syncwarp();
            if (lane < 3) mbar_arrive(BAR(B_EMPTY + 4 - w + lane));
            if (lane < 3 && w == 0) mbar_arrive(BAR(B_EMPTY + lane));
            float ds[4] = {}, da[4] = {}, db[4] = {};
            uint32_t* xo = act + RB_X1 + tile * 14336 + 7 * j * 256 + wi * 64 + lane;
#pragma unroll
            for (int g = 0; g < 7; g++) {
                const float2 ga = *(const float2*)(smem + M_G + (8 * g + 2 * q) * 4);
                x1p[2 * g] = pack2(fmaf(ga.x, ac[4 * g], bf_lo(xr[2 * g])), fmaf(ga.y, ac[4 * g + 1], bf_hi(xr[2 * g])));
                x1p[2 * g + 1] = pack2(fmaf(ga.x, ac[4 * g + 2], bf_lo(xr[2 * g + 1])), fmaf(ga.y, ac[4 * g + 3], bf_hi(xr[2 * g + 1])));
                st_relaxed(xo + g * 256, nz(x1p[2 * g])); st_relaxed(xo + g * 256 + 32, nz(x1p[2 * g + 1]));
                mma1688(ds, x1p[2 * g], x1p[2 * g + 1], 0x3F803F80u);
                mma1688(da, x1p[2 * g], x1p[2 * g + 1], x1p[2 * g]);
                mma1688(db, x1p[2 * g], x1p[2 * g + 1], x1p[2 * g + 1]);
            }
            const int src = (lane & ~3) | (lr >> 1);
            const float qa = __shfl_sync(~0u, (lr & 1) ? da[1] : da[0], src), qb = __shfl_sync(~0u, (lr & 1) ? db[3] : db[2], src);
            const float kk = (q & 1) ? ((q & 2) ? qb : qa) : ((q & 2) ? ds[2] : ds[0]);
            st_relaxed(act + RB_ST + ((tile * 8 + j) * 64 + 16 * wi + lr + 4 * (q & 2)) * 2 + (q & 1), nz(__float_as_uint(kk)));
            if (lane < 8) st_relaxed(g_flag + (8 * r + lane) * 192 + 128 + 32 * w + 4 * j + wi, epoch + 1);
        }
        PROFC(15);
        uint32_t h2a[32], h2b[24];
        {
            const int fa = pass_f(fs, 0), fb = pass_f(fs, 1), fc = pass_f(fs, 2);
            uint32_t* h2g = act + RB_H2 + (8 * w + 2 * wi) * 32 + lane;
            const uint32_t a0 = mkdesc(sb + OFF_Y + w * HALF, DT);
            {
                LnRow ca, cb;
                {
                    const uint32_t* sg = act + RB_ST + ((tile * 8 + 2 * q) * 64 + 16 * wi + lr) * 2;
                    uint2 u[4];
                    WAIT(B_FULLV + w, 1);
                    PROFC(16);
#pragma unroll
                    for (int i = 0; i < 4; i++) { const float2 v = lds2f(sb + OFF_X + X_STAT + w * 49152 + ((2 * q + (i >> 1)) * 64 + 16 * wi + lr + 8 * (i & 1)) * 8); u[i] = make_uint2(__float_as_uint(v.x), __float_as_uint(v.y)); }
                    while (__any_sync(~0u, min(min(min(u[0].x, u[0].y), min(u[1].x, u[1].y)), min(min(u[2].x, u[2].y), min(u[3].x, u[3].y))) == 0u)) {
#pragma unroll
                        for (int i = 0; i < 4; i++) u[i] = ld_relaxed2(sg + (i >> 1) * 128 + (i & 1) * 16);
                    }
                    warp_arrive(BAR(B_EMPTY + 3 + 3 * w));
                    float v[4] = {__uint_as_float(u[0].x) + __uint_as_float(u[2].x), __uint_as_float(u[0].y) + __uint_as_float(u[2].y),
                                  __uint_as_float(u[1].x) + __uint_as_float(u[3].x), __uint_as_float(u[1].y) + __uint_as_float(u[3].y)};
#pragma unroll
                    for (int i = 0; i < 4; i++) { v[i] += __shfl_xor_sync(~0u, v[i], 1); v[i] += __shfl_xor_sync(~0u, v[i], 2); }
                    ca = ln_coeffs(v[0] * (1.f / DM), v[1] * (1.f / DM));
                    cb = ln_coeffs(v[2] * (1.f / DM), v[3] * (1.f / DM));
                }
                const uint32_t ha = sb + OFF_Y + w * HALF + (lane >> 4) * 1024 + (2 * wi + ((lane >> 3) & 1)) * 128 + (lane & 7) * 16;
                const uint32_t sta = sb + M_ST + q * 16;
                const uint32_t* xg = act + RB_X1 + tile * 14336 + (lane >> 4) * 256 + wi * 64 + (lane & 15) * 4;
                uint32_t x[8];
                const uint32_t xs = sb + OFF_Y + w * HALF + (lane >> 4) * 1024 + wi * 256 + (lane & 15) * 16;
                uint4 st[2];
                auto load = [&](int s) {
                    if (s == 4) mbar_wait_c(BAR(B_XFULL + 4 + w), 1);
                    ldsm4(ha + s * 4096, x); ldsm4(ha + s * 4096 + 2048, x + 4);
                    st[0] = lds4(sta + s * 128); st[1] = lds4(sta + s * 128 + 64);
                };
                auto prep = [&](int s, uint32_t* f) {
                    if (__any_sync(~0u, min(min(min(x[0], x[1]), min(x[2], x[3])), min(min(x[4], x[5]), min(x[6], x[7]))) == 0u)) {
                        WG_WAIT(0);
                        x1_fix(xg, xs, s);
                        ldsm4(ha + s * 4096, x); ldsm4(ha + s * 4096 + 2048, x + 4);
                    }
#pragma unroll
                    for (int i = 0; i < 2; i++) {
                        f[4 * i] = ln_mod(ln_norm(x[4 * i], ca), st[i].x, st[i].y); f[4 * i + 1] = ln_mod(ln_norm(x[4 * i + 1], cb), st[i].x, st[i].y);
                        f[4 * i + 2] = ln_mod(ln_norm(x[4 * i + 2], ca), st[i].z, st[i].w); f[4 * i + 3] = ln_mod(ln_norm(x[4 * i + 3], cb), st[i].z, st[i].w);
                    }
                    if (s < 13) load(s + 1);
                    stsm4(ha + s * 4096, f[0], f[1], f[2], f[3]); stsm4(ha + s * 4096 + 2048, f[4], f[5], f[6], f[7]);
                };
                float ac[128];
                uint32_t fr[3][8];
                uint64_t bd = (DB128 & ~0xFFFFFFFFull) | mkdesc(sb, DB128);
                reg_def<128>(ac);
                WAIT(B_GFULL + 2 + w, 0);
                load(0);
                prep(0, fr[0]);
                PROFC(17);
#pragma unroll
                for (int s = 0; s < 14; s++) {
                    const uint32_t* f = fr[s % 3];
                    WAIT(B_FULL + g1_slot(s), s >= 7);
                    WG_FENCE();
                    wgmma_rl_256(ac, f[0], f[1], f[2], f[3], bd, s != 0);
                    wgmma_rl_256(ac, f[4], f[5], f[6], f[7], bd + 128, 1);
                    bd += s == 6 ? p.zero - 6 * 1024ull : 1024;
                    WG_COMMIT();
                    if (s < 13) prep(s + 1, fr[(s + 1) % 3]);
                    if (s > 0) { WG_WAIT(1); warp_arrive(BAR(B_EMPTY + g1_slot(s - 1))); }
                }
                fence_async_smem();
                PROFC(18);
                WG_WAIT(0);
                reg_fence<128>(ac);
                warp_arrive(BAR(B_EMPTY + 6));
#pragma unroll
                for (int g = 0; g < 16; g++) {
                    h2a[2 * g] = hmul2(pack2_relu(ac[4 * g], ac[4 * g + 1]), pack2(ac[64 + 4 * g], ac[64 + 4 * g + 1]));
                    h2a[2 * g + 1] = hmul2(pack2_relu(ac[4 * g + 2], ac[4 * g + 3]), pack2(ac[64 + 4 * g + 2], ac[64 + 4 * g + 3]));
                }
                bar_sync(1 + w, 128);
            }
            PROFC(19);
            {
                float ac[64];
                reg_def<64>(ac);
                const uint32_t bx = mkdesc(sb, dconst(8192, 1024, 1));
#pragma unroll 1
                for (int s = 0; s < 7; s++) {
                    WAIT(B_FULL + s, 0);
                    const uint32_t ad = a0 + s * 512, bd = bx + (slot_off(s) >> 4);
                    WG_FENCE();
#pragma unroll
                    for (int k = 0; k < 4; k++) wgmma_ss_128<DT, DB128>(ac, ad + k * 128, bd + k * 128, (s | k) != 0);
                    WG_COMMIT();
                    if (s == 1) {
#pragma unroll
                        for (int g = 0; g < 16; g++) { h2g[(fa / 8 + g) * 512] = h2a[2 * g]; h2g[(fa / 8 + g) * 512 + 32] = h2a[2 * g + 1]; }
                        warp_arrive(BAR(B_PUB + 6));
                    }
                    if (s > 0) { WG_WAIT(1); warp_arrive(BAR(B_EMPTY + s - 1)); }
                }
                WG_WAIT(0);
                reg_fence<64>(ac);
                warp_arrive(BAR(B_EMPTY + 6));
#pragma unroll
                for (int g = 0; g < 8; g++) {
                    h2b[2 * g] = hmul2(pack2_relu(ac[4 * g], ac[4 * g + 1]), pack2(ac[32 + 4 * g], ac[32 + 4 * g + 1]));
                    h2b[2 * g + 1] = hmul2(pack2_relu(ac[4 * g + 2], ac[4 * g + 3]), pack2(ac[32 + 4 * g + 2], ac[32 + 4 * g + 3]));
                }
            }
            PROFC(27);
            {
                float ac[32];
                reg_def<32>(ac);
                const uint32_t bx = mkdesc(sb, dconst(4096, 512, 2));
#pragma unroll 1
                for (int s = 0; s < 7; s++) {
                    WAIT(B_FULL + (s >> 1), 1);
                    const uint32_t ad = a0 + s * 512, bd = bx + s * 512;
                    WG_FENCE();
#pragma unroll
                    for (int k = 0; k < 4; k++) wgmma_ss_64<DT, dconst(4096, 512, 2)>(ac, ad + k * 128, bd + k * 64, (s | k) != 0);
                    WG_COMMIT();
                    if (s == 1) {
#pragma unroll
                        for (int g = 0; g < 8; g++) { h2g[(fb / 8 + g) * 512] = h2b[2 * g]; h2g[(fb / 8 + g) * 512 + 32] = h2b[2 * g + 1]; }
                        warp_arrive(BAR(B_PUB + 7));
                    }
                    if (s > 0 && !(s & 1)) {
                        WG_WAIT(1);
                        __syncwarp();
                        if (lane < 3) mbar_arrive(BAR(B_EMPTY + (s >> 1) - 1 + (lane ? 4 + 3 * lane : 0)));
                    }
                }
                WG_WAIT(0);
                reg_fence<32>(ac);
                PROFC(20);
#pragma unroll
                for (int g = 0; g < 4; g++) {
                    h2b[16 + 2 * g] = hmul2(pack2_relu(ac[4 * g], ac[4 * g + 1]), pack2(ac[16 + 4 * g], ac[16 + 4 * g + 1]));
                    h2b[16 + 2 * g + 1] = hmul2(pack2_relu(ac[4 * g + 2], ac[4 * g + 3]), pack2(ac[16 + 4 * g + 2], ac[16 + 4 * g + 3]));
                    h2g[(fc / 8 + g) * 512] = h2b[16 + 2 * g]; h2g[(fc / 8 + g) * 512 + 32] = h2b[16 + 2 * g + 1];
                }
                warp_arrive(BAR(B_PUB + 8));
                asm volatile("barrier.cluster.wait.aligned;" ::: "memory");
                if (lane == 0) {
                    uint32_t rb;
                    asm volatile("mapa.shared::cluster.u32 %0, %1, %2;" : "=r"(rb) : "r"(BAR(B_PEER)), "r"(kh ^ 1));
                    asm volatile("mbarrier.arrive.relaxed.cluster.shared::cluster.b64 _, [%0];" ::"r"(rb) : "memory");
                }
            }
        }
        PROFC(21);
        {
            float ac[56];
            reg_def<56>(ac);
            constexpr uint64_t DAN = dconst(2048, 128, 0);
            constexpr uint64_t DW = dconst(128, 512, 0);
            const uint32_t bx = mkdesc(sb, DW);
#pragma unroll
            for (int e = 3; e < 7; e++) {
                if (e > 3) WAIT(B_FULL + e, 1);
                const uint64_t bd = ((DW & ~0xFFFFFFFFull) | bx) + (slot_off(e) >> 4);
                const uint32_t* hh = e == 3 ? h2b + 8 : e < 6 ? h2a + 16 * (e - 4) : h2b;
                WG_FENCE();
#pragma unroll
                for (int k = e == 3 ? 2 : 0; k < 4; k++) wgmma_rl_112(ac, hh[4 * k], hh[4 * k + 1], hh[4 * k + 2], hh[4 * k + 3], bd + (k >> 1) * 512 + (k & 1) * 16, e > 3 || k > 2);
                WG_COMMIT();
                if (e > 3) { WG_WAIT(1); warp_arrive(BAR(B_EMPTY + e - 1)); }
            }
            PROFC(22);
            const uint32_t ax = mkdesc(sb + 8192 + w * 1024, DAN);
            uint32_t eb_ = BAR(B_EMPTY + 6);
            uint64_t ord = RING_ORDER;
#pragma unroll 1
            for (int e = 0; e < 21; e++) {
                const uint32_t sl = ord & 15, so = slot_off(sl) >> 4;
                ord = e == 12 ? RING_ORDER : ord >> 4;
                mbar_wait_c(BAR(B_FULL + sl), e >= 13);
                WG_FENCE();
                wgmma_ss_112<DAN, DW>(ac, ax + so, bx + so, 1);
                wgmma_ss_112<DAN, DW>(ac, ax + so + 256, bx + so + 16, 1);
                WG_COMMIT();
                WG_WAIT(1);
                warp_arrive(eb_);
                eb_ = BAR(B_EMPTY + sl);
            }
            mbar_wait_cluster(BAR(B_PEER), 0);
            WG_WAIT(0);
            reg_fence<56>(ac);
            PROFC(24);
            uint32_t rdst, rbar;
            asm volatile("mapa.shared::cluster.u32 %0, %1, %2;" : "=r"(rdst) : "r"(sb + OFF_Y + Y_XCH + w * HALF + t * 16), "r"(kh ^ 1));
            asm volatile("mapa.shared::cluster.u32 %0, %1, %2;" : "=r"(rbar) : "r"(BAR(B_XCH + w)), "r"(kh ^ 1));
#pragma unroll
            for (int g = 0; g < 3; g++)
                asm volatile("st.async.shared::cluster.mbarrier::complete_tx::bytes.v4.b32 [%0], {%1,%2,%3,%4}, [%5];" ::"r"(rdst + g * 2048),
                             "r"(pack2(ac[28 + 8 * g], ac[29 + 8 * g])), "r"(pack2(ac[30 + 8 * g], ac[31 + 8 * g])), "r"(pack2(ac[32 + 8 * g], ac[33 + 8 * g])),
                             "r"(pack2(ac[34 + 8 * g], ac[35 + 8 * g])), "r"(rbar) : "memory");
            asm volatile("st.async.shared::cluster.mbarrier::complete_tx::bytes.v2.b32 [%0], {%1,%2}, [%3];" ::"r"(rdst + 6144 - t * 8),
                         "r"(pack2(ac[52], ac[53])), "r"(pack2(ac[54], ac[55])), "r"(rbar) : "memory");
            mbar_wait_cluster(BAR(B_XCH + w), 0);
            PROFC(25);
            uint32_t op[14], rv[14];
#pragma unroll
            for (int g = 0; g < 3; g++) *(uint4*)(rv + 4 * g) = *(const uint4*)(smem + OFF_Y + Y_XCH + w * HALF + t * 16 + g * 2048);
            *(uint2*)(rv + 12) = *(const uint2*)(smem + OFF_Y + Y_XCH + w * HALF + 6144 + t * 8);
#pragma unroll
            for (int i = 0; i < 14; i++) {
                const float2 gb = *(const float2*)(smem + M_G + 224 + (8 * (i >> 1) + 2 * q) * 4);
                op[i] = pack2(fmaf(gb.x, ac[2 * i] + bf_lo(rv[i]), bf_lo(x1p[i])), fmaf(gb.y, ac[2 * i + 1] + bf_hi(rv[i]), bf_hi(x1p[i])));
            }
            WAIT(B_EMPTY + 4, 1);
            const uint32_t oc = sb + OUT_STAGE + warp * 1792;
            const uint32_t oa = oc + (((lane >> 3) & 1) * 8 + (lane & 7)) * 112 + (lane >> 4) * 16;
            stsm4(oa, op[0], op[1], op[2], op[3]); stsm4(oa + 32, op[4], op[5], op[6], op[7]); stsm4(oa + 64, op[8], op[9], op[10], op[11]);
            asm volatile("stmatrix.sync.aligned.m8n8.x2.shared.b16 [%0], {%1,%2};" ::"r"(oa + 96), "r"(op[12]), "r"(op[13]));
            fence_async_smem();
            __syncwarp();
            asm volatile("{\n.reg .pred p;\nelect.sync _|p, 0xffffffff;\n@p cp.async.bulk.tensor.3d.global.shared::cta.bulk_group [%0, {%2, %3, %4}], [%1];\n"
                         "cp.async.bulk.commit_group;\ncp.async.bulk.wait_group.read 0;\n}" ::"l"(&p.om), "r"(oc), "r"(56 * j), "r"(128 * r + 64 * w + 16 * wi), "r"(0) : "memory");
        }
        PROFC(26);
        bar_sync(1 + w, 128);
        if (wi == 0) warp_arrive(BAR(B_DONE));
        return;
    }
    helper_late(p, r, j, warp PROF_ARGS);
}

#undef act
typedef CUresult (*EncodeFn)(CUtensorMap*, CUtensorMapDataType, cuuint32_t, void*, const cuuint64_t*, const cuuint64_t*, const cuuint32_t*,
                             const cuuint32_t*, CUtensorMapInterleave, CUtensorMapSwizzle, CUtensorMapL2promotion, CUtensorMapFloatOOBfill);

static void make_map(EncodeFn fn, CUtensorMap* m, const void* ptr, uint64_t d0, uint64_t d1, uint64_t d2, uint64_t s1, uint64_t s2,
                     uint32_t b0, uint32_t b1, uint32_t b2, CUtensorMapSwizzle sw) {
    cuuint64_t dims[3] = {d0, d1, d2}, strides[2] = {s1, s2};
    cuuint32_t box[3] = {b0, b1, b2}, es[3] = {1, 1, 1};
    CUresult rc = fn(m, CU_TENSOR_MAP_DATA_TYPE_BFLOAT16, 3, (void*)ptr, dims, strides, box, es, CU_TENSOR_MAP_INTERLEAVE_NONE, sw,
                     CU_TENSOR_MAP_L2_PROMOTION_L2_128B, CU_TENSOR_MAP_FLOAT_OOB_FILL_NONE);
    (void)rc;
}

extern "C" void kernel_launch(void* const* d_in, const int* in_sizes, int n_in, void* d_out, int out_size) {
    (void)in_sizes; (void)n_in; (void)out_size;
    static EncodeFn fn = nullptr;
    static uint32_t* act_base = nullptr;
    if (!fn) {
        cudaDriverEntryPointQueryResult st;
        cudaGetDriverEntryPoint("cuTensorMapEncodeTiled", (void**)&fn, cudaEnableDefault, &st);
        void* a = nullptr;
        cudaGetSymbolAddress(&a, g_act);
        act_base = (uint32_t*)(((uintptr_t)a + 0xFFFFF) & ~(uintptr_t)0xFFFFF);
        cudaFuncSetAttribute(fused_block_kernel, cudaFuncAttributeMaxDynamicSharedMemorySize, SMEM_BYTES);
    }
    Params p;
    p.x = (const bf16*)d_in[0];
    const bf16* wqkv = (const bf16*)d_in[1];
    p.wqkv = wqkv;
    p.wop = (const bf16*)d_in[2];
    p.wg = (const bf16*)d_in[4];
    p.wu = (const bf16*)d_in[5];
    p.wd = (const bf16*)d_in[6];
    p.c = (const bf16*)d_in[7];
    p.wmod = (const bf16*)d_in[8];
    p.out = (bf16*)d_out;
    p.zero = 0;
    p.actb = act_base;
    make_map(fn, &p.wm, p.wmod, 2688, 448, 1, 5376, 5376 * 448, 16, 224, 1, CU_TENSOR_MAP_SWIZZLE_NONE);
    make_map(fn, &p.wm2, p.wmod, 2688, 448, 1, 5376, 5376 * 448, 32, 224, 1, CU_TENSOR_MAP_SWIZZLE_NONE);
    make_map(fn, &p.om, p.out, 448, 2048, 1, 896, 896 * 2048, 56, 16, 1, CU_TENSOR_MAP_SWIZZLE_NONE);
    make_map(fn, &p.xm, p.x, 448, 2048, 1, 896, 896 * 2048, 64, 128, 1, CU_TENSOR_MAP_SWIZZLE_128B);
    make_map(fn, &p.qkv, wqkv, 1344, 448, 1, 2688, 2688 * 448, 64, 224, 1, CU_TENSOR_MAP_SWIZZLE_128B);
    make_map(fn, &p.wo, p.wop, 448, 448, 1, 896, 896 * 448, 64, 224, 1, CU_TENSOR_MAP_SWIZZLE_128B);
    make_map(fn, &p.ga, p.wg, 64, 448, 28, 3584, 128, 64, 32, 2, CU_TENSOR_MAP_SWIZZLE_128B);
    make_map(fn, &p.ua, p.wu, 64, 448, 28, 3584, 128, 64, 32, 2, CU_TENSOR_MAP_SWIZZLE_128B);
    make_map(fn, &p.gb, p.wg, 64, 448, 28, 3584, 128, 64, 64, 1, CU_TENSOR_MAP_SWIZZLE_128B);
    make_map(fn, &p.ub, p.wu, 64, 448, 28, 3584, 128, 64, 64, 1, CU_TENSOR_MAP_SWIZZLE_128B);
    make_map(fn, &p.gc, p.wg, 32, 448, 56, 3584, 64, 32, 64, 1, CU_TENSOR_MAP_SWIZZLE_64B);
    make_map(fn, &p.uc, p.wu, 32, 448, 56, 3584, 64, 32, 64, 1, CU_TENSOR_MAP_SWIZZLE_64B);
    make_map(fn, &p.dn, p.wd, 8, 1792, 56, 896, 16, 8, 32, 7, CU_TENSOR_MAP_SWIZZLE_NONE);
    fused_block_kernel<<<NCTA, 384, SMEM_BYTES>>>(p);
}
```

```cpp
#include <cuda_runtime.h>
#include <cuda_bf16.h>
#include <cuda.h>
#include <stdint.h>

typedef __nv_bfloat16 bf16;

template<uint64_t CA, uint64_t CB> __device__ __forceinline__ void wgmma_sk_160(float* d, uint32_t da, uint32_t db, int sd) {
  asm volatile("{\n.reg .pred p;\n.reg .b64 a, b;\nsetp.ne.b32 p, %82, 0;\nmov.b64 a, {%80, %83};\nmov.b64 b, {%81, %84};\n"
    "wgmma.mma_async.sync.aligned.m64n160k16.f32.bf16.bf16 {%0,%1,%2,%3,%4,%5,%6,%7,%8,%9,%10,%11,%12,%13,%14,%15,%16,%17,%18,%19,%20,%21,%22,%23,%24,%25,%26,%27,%28,%29,%30,%31,%32,%33,%34,%35,%36,%37,%38,%39,%40,%41,%42,%43,%44,%45,%46,%47,%48,%49,%50,%51,%52,%53,%54,%55,%56,%57,%58,%59,%60,%61,%62,%63,%64,%65,%66,%67,%68,%69,%70,%71,%72,%73,%74,%75,%76,%77,%78,%79}, a, b, p, 1, 1, 0, 0;\n}\n"
    : "+f"(d[0]),"+f"(d[1]),"+f"(d[2]),"+f"(d[3]),"+f"(d[4]),"+f"(d[5]),"+f"(d[6]),"+f"(d[7]),"+f"(d[8]),"+f"(d[9]),"+f"(d[10]),"+f"(d[11]),"+f"(d[12]),"+f"(d[13]),"+f"(d[14]),"+f"(d[15]),"+f"(d[16]),"+f"(d[17]),"+f"(d[18]),"+f"(d[19]),"+f"(d[20]),"+f"(d[21]),"+f"(d[22]),"+f"(d[23]),"+f"(d[24]),"+f"(d[25]),"+f"(d[26]),"+f"(d[27]),"+f"(d[28]),"+f"(d[29]),"+f"(d[30]),"+f"(d[31]),"+f"(d[32]),"+f"(d[33]),"+f"(d[34]),"+f"(d[35]),"+f"(d[36]),"+f"(d[37]),"+f"(d[38]),"+f"(d[39]),"+f"(d[40]),"+f"(d[41]),"+f"(d[42]),"+f"(d[43]),"+f"(d[44]),"+f"(d[45]),"+f"(d[46]),"+f"(d[47]),"+f"(d[48]),"+f"(d[49]),"+f"(d[50]),"+f"(d[51]),"+f"(d[52]),"+f"(d[53]),"+f"(d[54]),"+f"(d[55]),"+f"(d[56]),"+f"(d[57]),"+f"(d[58]),"+f"(d[59]),"+f"(d[60]),"+f"(d[61]),"+f"(d[62]),"+f"(d[63]),"+f"(d[64]),"+f"(d[65]),"+f"(d[66]),"+f"(d[67]),"+f"(d[68]),"+f"(d[69]),"+f"(d[70]),"+f"(d[71]),"+f"(d[72]),"+f"(d[73]),"+f"(d[74]),"+f"(d[75]),"+f"(d[76]),"+f"(d[77]),"+f"(d[78]),"+f"(d[79])
    : "r"(da), "r"(db), "r"(sd), "n"((uint32_t)(CA >> 32)), "n"((uint32_t)(CB >> 32)));
}
__device__ __forceinline__ void wgmma_rl_56(float* d, uint32_t a0, uint32_t a1, uint32_t a2, uint32_t a3, uint64_t db, int sd) {
  asm volatile("{\n.reg .pred p;\nsetp.ne.b32 p, %33, 0;\n"
    "wgmma.mma_async.sync.aligned.m64n56k16.f32.bf16.bf16 {%0,%1,%2,%3,%4,%5,%6,%7,%8,%9,%10,%11,%12,%13,%14,%15,%16,%17,%18,%19,%20,%21,%22,%23,%24,%25,%26,%27}, {%28,%29,%30,%31}, %32, p, 1, 1, 1;\n}\n"
    : "+f"(d[0]),"+f"(d[1]),"+f"(d[2]),"+f"(d[3]),"+f"(d[4]),"+f"(d[5]),"+f"(d[6]),"+f"(d[7]),"+f"(d[8]),"+f"(d[9]),"+f"(d[10]),"+f"(d[11]),"+f"(d[12]),"+f"(d[13]),"+f"(d[14]),"+f"(d[15]),"+f"(d[16]),"+f"(d[17]),"+f"(d[18]),"+f"(d[19]),"+f"(d[20]),"+f"(d[21]),"+f"(d[22]),"+f"(d[23]),"+f"(d[24]),"+f"(d[25]),"+f"(d[26]),"+f"(d[27])
    : "r"(a0), "r"(a1), "r"(a2), "r"(a3), "l"(db), "r"(sd));
}
template<uint64_t CA, uint64_t CB> __device__ __forceinline__ void wgmma_ss_56(float* d, uint32_t da, uint32_t db, int sd) {
  asm volatile("{\n.reg .pred p;\n.reg .b64 a, b;\nsetp.ne.b32 p, %30, 0;\nmov.b64 a, {%28, %31};\nmov.b64 b, {%29, %32};\n"
    "wgmma.mma_async.sync.aligned.m64n56k16.f32.bf16.bf16 {%0,%1,%2,%3,%4,%5,%6,%7,%8,%9,%10,%11,%12,%13,%14,%15,%16,%17,%18,%19,%20,%21,%22,%23,%24,%25,%26,%27}, a, b, p, 1, 1, 0, 1;\n}\n"
    : "+f"(d[0]),"+f"(d[1]),"+f"(d[2]),"+f"(d[3]),"+f"(d[4]),"+f"(d[5]),"+f"(d[6]),"+f"(d[7]),"+f"(d[8]),"+f"(d[9]),"+f"(d[10]),"+f"(d[11]),"+f"(d[12]),"+f"(d[13]),"+f"(d[14]),"+f"(d[15]),"+f"(d[16]),"+f"(d[17]),"+f"(d[18]),"+f"(d[19]),"+f"(d[20]),"+f"(d[21]),"+f"(d[22]),"+f"(d[23]),"+f"(d[24]),"+f"(d[25]),"+f"(d[26]),"+f"(d[27])
    : "r"(da), "r"(db), "r"(sd), "n"((uint32_t)(CA >> 32)), "n"((uint32_t)(CB >> 32)));
}
__device__ __forceinline__ void wgmma_rl_256(float* d, uint32_t a0, uint32_t a1, uint32_t a2, uint32_t a3, uint64_t db, int sd) {
  asm volatile("{\n.reg .pred p;\nsetp.ne.b32 p, %133, 0;\n"
    "wgmma.mma_async.sync.aligned.m64n256k16.f32.bf16.bf16 {%0,%1,%2,%3,%4,%5,%6,%7,%8,%9,%10,%11,%12,%13,%14,%15,%16,%17,%18,%19,%20,%21,%22,%23,%24,%25,%26,%27,%28,%29,%30,%31,%32,%33,%34,%35,%36,%37,%38,%39,%40,%41,%42,%43,%44,%45,%46,%47,%48,%49,%50,%51,%52,%53,%54,%55,%56,%57,%58,%59,%60,%61,%62,%63,%64,%65,%66,%67,%68,%69,%70,%71,%72,%73,%74,%75,%76,%77,%78,%79,%80,%81,%82,%83,%84,%85,%86,%87,%88,%89,%90,%91,%92,%93,%94,%95,%96,%97,%98,%99,%100,%101,%102,%103,%104,%105,%106,%107,%108,%109,%110,%111,%112,%113,%114,%115,%116,%117,%118,%119,%120,%121,%122,%123,%124,%125,%126,%127}, {%128,%129,%130,%131}, %132, p, 1, 1, 1;\n}\n"
    : "+f"(d[0]),"+f"(d[1]),"+f"(d[2]),"+f"(d[3]),"+f"(d[4]),"+f"(d[5]),"+f"(d[6]),"+f"(d[7]),"+f"(d[8]),"+f"(d[9]),"+f"(d[10]),"+f"(d[11]),"+f"(d[12]),"+f"(d[13]),"+f"(d[14]),"+f"(d[15]),"+f"(d[16]),"+f"(d[17]),"+f"(d[18]),"+f"(d[19]),"+f"(d[20]),"+f"(d[21]),"+f"(d[22]),"+f"(d[23]),"+f"(d[24]),"+f"(d[25]),"+f"(d[26]),"+f"(d[27]),"+f"(d[28]),"+f"(d[29]),"+f"(d[30]),"+f"(d[31]),"+f"(d[32]),"+f"(d[33]),"+f"(d[34]),"+f"(d[35]),"+f"(d[36]),"+f"(d[37]),"+f"(d[38]),"+f"(d[39]),"+f"(d[40]),"+f"(d[41]),"+f"(d[42]),"+f"(d[43]),"+f"(d[44]),"+f"(d[45]),"+f"(d[46]),"+f"(d[47]),"+f"(d[48]),"+f"(d[49]),"+f"(d[50]),"+f"(d[51]),"+f"(d[52]),"+f"(d[53]),"+f"(d[54]),"+f"(d[55]),"+f"(d[56]),"+f"(d[57]),"+f"(d[58]),"+f"(d[59]),"+f"(d[60]),"+f"(d[61]),"+f"(d[62]),"+f"(d[63]),"+f"(d[64]),"+f"(d[65]),"+f"(d[66]),"+f"(d[67]),"+f"(d[68]),"+f"(d[69]),"+f"(d[70]),"+f"(d[71]),"+f"(d[72]),"+f"(d[73]),"+f"(d[74]),"+f"(d[75]),"+f"(d[76]),"+f"(d[77]),"+f"(d[78]),"+f"(d[79]),"+f"(d[80]),"+f"(d[81]),"+f"(d[82]),"+f"(d[83]),"+f"(d[84]),"+f"(d[85]),"+f"(d[86]),"+f"(d[87]),"+f"(d[88]),"+f"(d[89]),"+f"(d[90]),"+f"(d[91]),"+f"(d[92]),"+f"(d[93]),"+f"(d[94]),"+f"(d[95]),"+f"(d[96]),"+f"(d[97]),"+f"(d[98]),"+f"(d[99]),"+f"(d[100]),"+f"(d[101]),"+f"(d[102]),"+f"(d[103]),"+f"(d[104]),"+f"(d[105]),"+f"(d[106]),"+f"(d[107]),"+f"(d[108]),"+f"(d[109]),"+f"(d[110]),"+f"(d[111]),"+f"(d[112]),"+f"(d[113]),"+f"(d[114]),"+f"(d[115]),"+f"(d[116]),"+f"(d[117]),"+f"(d[118]),"+f"(d[119]),"+f"(d[120]),"+f"(d[121]),"+f"(d[122]),"+f"(d[123]),"+f"(d[124]),"+f"(d[125]),"+f"(d[126]),"+f"(d[127])
    : "r"(a0), "r"(a1), "r"(a2), "r"(a3), "l"(db), "r"(sd));
}
template<uint64_t CA, uint64_t CB> __device__ __forceinline__ void wgmma_ss_128(float* d, uint32_t da, uint32_t db, int sd) {
  asm volatile("{\n.reg .pred p;\n.reg .b64 a, b;\nsetp.ne.b32 p, %66, 0;\nmov.b64 a, {%64, %67};\nmov.b64 b, {%65, %68};\n"
    "wgmma.mma_async.sync.aligned.m64n128k16.f32.bf16.bf16 {%0,%1,%2,%3,%4,%5,%6,%7,%8,%9,%10,%11,%12,%13,%14,%15,%16,%17,%18,%19,%20,%21,%22,%23,%24,%25,%26,%27,%28,%29,%30,%31,%32,%33,%34,%35,%36,%37,%38,%39,%40,%41,%42,%43,%44,%45,%46,%47,%48,%49,%50,%51,%52,%53,%54,%55,%56,%57,%58,%59,%60,%61,%62,%63}, a, b, p, 1, 1, 0, 1;\n}\n"
    : "+f"(d[0]),"+f"(d[1]),"+f"(d[2]),"+f"(d[3]),"+f"(d[4]),"+f"(d[5]),"+f"(d[6]),"+f"(d[7]),"+f"(d[8]),"+f"(d[9]),"+f"(d[10]),"+f"(d[11]),"+f"(d[12]),"+f"(d[13]),"+f"(d[14]),"+f"(d[15]),"+f"(d[16]),"+f"(d[17]),"+f"(d[18]),"+f"(d[19]),"+f"(d[20]),"+f"(d[21]),"+f"(d[22]),"+f"(d[23]),"+f"(d[24]),"+f"(d[25]),"+f"(d[26]),"+f"(d[27]),"+f"(d[28]),"+f"(d[29]),"+f"(d[30]),"+f"(d[31]),"+f"(d[32]),"+f"(d[33]),"+f"(d[34]),"+f"(d[35]),"+f"(d[36]),"+f"(d[37]),"+f"(d[38]),"+f"(d[39]),"+f"(d[40]),"+f"(d[41]),"+f"(d[42]),"+f"(d[43]),"+f"(d[44]),"+f"(d[45]),"+f"(d[46]),"+f"(d[47]),"+f"(d[48]),"+f"(d[49]),"+f"(d[50]),"+f"(d[51]),"+f"(d[52]),"+f"(d[53]),"+f"(d[54]),"+f"(d[55]),"+f"(d[56]),"+f"(d[57]),"+f"(d[58]),"+f"(d[59]),"+f"(d[60]),"+f"(d[61]),"+f"(d[62]),"+f"(d[63])
    : "r"(da), "r"(db), "r"(sd), "n"((uint32_t)(CA >> 32)), "n"((uint32_t)(CB >> 32)));
}
template<uint64_t CA, uint64_t CB> __device__ __forceinline__ void wgmma_ss_64(float* d, uint32_t da, uint32_t db, int sd) {
  asm volatile("{\n.reg .pred p;\n.reg .b64 a, b;\nsetp.ne.b32 p, %34, 0;\nmov.b64 a, {%32, %35};\nmov.b64 b, {%33, %36};\n"
    "wgmma.mma_async.sync.aligned.m64n64k16.f32.bf16.bf16 {%0,%1,%2,%3,%4,%5,%6,%7,%8,%9,%10,%11,%12,%13,%14,%15,%16,%17,%18,%19,%20,%21,%22,%23,%24,%25,%26,%27,%28,%29,%30,%31}, a, b, p, 1, 1, 0, 1;\n}\n"
    : "+f"(d[0]),"+f"(d[1]),"+f"(d[2]),"+f"(d[3]),"+f"(d[4]),"+f"(d[5]),"+f"(d[6]),"+f"(d[7]),"+f"(d[8]),"+f"(d[9]),"+f"(d[10]),"+f"(d[11]),"+f"(d[12]),"+f"(d[13]),"+f"(d[14]),"+f"(d[15]),"+f"(d[16]),"+f"(d[17]),"+f"(d[18]),"+f"(d[19]),"+f"(d[20]),"+f"(d[21]),"+f"(d[22]),"+f"(d[23]),"+f"(d[24]),"+f"(d[25]),"+f"(d[26]),"+f"(d[27]),"+f"(d[28]),"+f"(d[29]),"+f"(d[30]),"+f"(d[31])
    : "r"(da), "r"(db), "r"(sd), "n"((uint32_t)(CA >> 32)), "n"((uint32_t)(CB >> 32)));
}
template<uint64_t CA, uint64_t CB> __device__ __forceinline__ void wgmma_ss_112(float* d, uint32_t da, uint32_t db, int sd) {
  asm volatile("{\n.reg .pred p;\n.reg .b64 a, b;\nsetp.ne.b32 p, %58, 0;\nmov.b64 a, {%56, %59};\nmov.b64 b, {%57, %60};\n"
    "wgmma.mma_async.sync.aligned.m64n112k16.f32.bf16.bf16 {%0,%1,%2,%3,%4,%5,%6,%7,%8,%9,%10,%11,%12,%13,%14,%15,%16,%17,%18,%19,%20,%21,%22,%23,%24,%25,%26,%27,%28,%29,%30,%31,%32,%33,%34,%35,%36,%37,%38,%39,%40,%41,%42,%43,%44,%45,%46,%47,%48,%49,%50,%51,%52,%53,%54,%55}, a, b, p, 1, 1, 0, 1;\n}\n"
    : "+f"(d[0]),"+f"(d[1]),"+f"(d[2]),"+f"(d[3]),"+f"(d[4]),"+f"(d[5]),"+f"(d[6]),"+f"(d[7]),"+f"(d[8]),"+f"(d[9]),"+f"(d[10]),"+f"(d[11]),"+f"(d[12]),"+f"(d[13]),"+f"(d[14]),"+f"(d[15]),"+f"(d[16]),"+f"(d[17]),"+f"(d[18]),"+f"(d[19]),"+f"(d[20]),"+f"(d[21]),"+f"(d[22]),"+f"(d[23]),"+f"(d[24]),"+f"(d[25]),"+f"(d[26]),"+f"(d[27]),"+f"(d[28]),"+f"(d[29]),"+f"(d[30]),"+f"(d[31]),"+f"(d[32]),"+f"(d[33]),"+f"(d[34]),"+f"(d[35]),"+f"(d[36]),"+f"(d[37]),"+f"(d[38]),"+f"(d[39]),"+f"(d[40]),"+f"(d[41]),"+f"(d[42]),"+f"(d[43]),"+f"(d[44]),"+f"(d[45]),"+f"(d[46]),"+f"(d[47]),"+f"(d[48]),"+f"(d[49]),"+f"(d[50]),"+f"(d[51]),"+f"(d[52]),"+f"(d[53]),"+f"(d[54]),"+f"(d[55])
    : "r"(da), "r"(db), "r"(sd), "n"((uint32_t)(CA >> 32)), "n"((uint32_t)(CB >> 32)));
}
__device__ __forceinline__ void wgmma_rl_112(float* d, uint32_t a0, uint32_t a1, uint32_t a2, uint32_t a3, uint64_t db, int sd) {
  asm volatile("{\n.reg .pred p;\nsetp.ne.b32 p, %61, 0;\n"
    "wgmma.mma_async.sync.aligned.m64n112k16.f32.bf16.bf16 {%0,%1,%2,%3,%4,%5,%6,%7,%8,%9,%10,%11,%12,%13,%14,%15,%16,%17,%18,%19,%20,%21,%22,%23,%24,%25,%26,%27,%28,%29,%30,%31,%32,%33,%34,%35,%36,%37,%38,%39,%40,%41,%42,%43,%44,%45,%46,%47,%48,%49,%50,%51,%52,%53,%54,%55}, {%56,%57,%58,%59}, %60, p, 1, 1, 1;\n}\n"
    : "+f"(d[0]),"+f"(d[1]),"+f"(d[2]),"+f"(d[3]),"+f"(d[4]),"+f"(d[5]),"+f"(d[6]),"+f"(d[7]),"+f"(d[8]),"+f"(d[9]),"+f"(d[10]),"+f"(d[11]),"+f"(d[12]),"+f"(d[13]),"+f"(d[14]),"+f"(d[15]),"+f"(d[16]),"+f"(d[17]),"+f"(d[18]),"+f"(d[19]),"+f"(d[20]),"+f"(d[21]),"+f"(d[22]),"+f"(d[23]),"+f"(d[24]),"+f"(d[25]),"+f"(d[26]),"+f"(d[27]),"+f"(d[28]),"+f"(d[29]),"+f"(d[30]),"+f"(d[31]),"+f"(d[32]),"+f"(d[33]),"+f"(d[34]),"+f"(d[35]),"+f"(d[36]),"+f"(d[37]),"+f"(d[38]),"+f"(d[39]),"+f"(d[40]),"+f"(d[41]),"+f"(d[42]),"+f"(d[43]),"+f"(d[44]),"+f"(d[45]),"+f"(d[46]),"+f"(d[47]),"+f"(d[48]),"+f"(d[49]),"+f"(d[50]),"+f"(d[51]),"+f"(d[52]),"+f"(d[53]),"+f"(d[54]),"+f"(d[55])
    : "r"(a0), "r"(a1), "r"(a2), "r"(a3), "l"(db), "r"(sd));
}

constexpr int DM = 448;
constexpr int NCTA = 128;
#define WIN 5
#define NPRE 14
#define VPRE 3
constexpr int SPIN_LIMIT = 1 << 22;

constexpr uint32_t OFF_X = 0, OFF_Y = 114688, OFF_MISC = 229376, SMEM_BYTES = 232448;
constexpr uint32_t Y_VR = 0, Y_K = 28672, Y_KOWN = 57344, Y_VOWN = 71680, Y_Q = 86016, Y_CELL = 102400;
constexpr uint32_t HALF = 57344;
constexpr uint32_t OUT_STAGE = 4 * 16384;
constexpr uint32_t M_BAR = OFF_MISC;
constexpr uint32_t M_ST = OFF_MISC + 512;
constexpr uint32_t M_G = OFF_MISC + 2304;
constexpr uint32_t M_EPOCH = OFF_MISC + 3040;
enum { B_XFULL = 0, B_FULLK = 7, B_FULLV = 8, B_FULLQ, B_KRFULL, B_VRFULL, B_WOFULL, B_XCH, B_MOD1 = 15, B_FULL = 16, B_WMFULL = 30,
       B_EMPTY = 32, B_PEER = 45, B_EPOCH,
       B_PUB = 47,
       B_XFREE = B_PUB + 4, B_GEMV,
       B_WMFREE = 56, B_HRDY, B_GFULL = B_HRDY + 3, B_DONE = 31 };

__device__ uint32_t g_ticket;
__device__ __align__(128) uint32_t g_mod[8 * 6 * DM];
__device__ __align__(128) uint32_t g_flag[144 * 192];
constexpr int RB_WORDS = 262144, RB_KV = 0, RB_O = 57344, RB_X1 = 86016, RB_H2 = 143360, RB_ST = 258048;
__device__ __align__(128) uint32_t g_act[17 * RB_WORDS];
__device__ __align__(128) uint32_t g_wd[56 * 4 * 1792];
#define PROFH(id)
#define PROFH1(id)
#define PROFC(id)

struct alignas(64) Params {
    CUtensorMap wm, wm2, om, xm, qkv, wo, ga, ua, gb, ub, gc, uc, dn, xr;
    const bf16 *x, *c, *wqkv, *wmod, *wg, *wu, *wd, *wop;
    bf16* out;
    uint32_t* actb;
    uint32_t zero;
};

__device__ __forceinline__ void mbar_init(uint32_t bar, int cnt) { asm volatile("mbarrier.init.shared::cta.b64 [%0], %1;" ::"r"(bar), "r"(cnt) : "memory"); }
__device__ __forceinline__ void mbar_arrive(uint32_t bar) { asm volatile("mbarrier.arrive.shared::cta.b64 _, [%0];" ::"r"(bar) : "memory"); }
__device__ __forceinline__ void mbar_wait(uint32_t bar, uint32_t parity) {
    uint32_t ok; int n = 0;
    do {
        asm volatile("{\n.reg .pred p;\nmbarrier.try_wait.parity.shared::cta.b64 p, [%1], %2;\nselp.u32 %0, 1, 0, p;\n}" : "=r"(ok) : "r"(bar), "r"(parity) : "memory");
        if (++n > SPIN_LIMIT) __trap();
    } while (!ok);
}
__device__ __forceinline__ void mbar_wait_c(uint32_t bar, uint32_t parity) {
    asm volatile("{\n.reg .pred p;\nWL:\nmbarrier.try_wait.parity.shared::cta.b64 p, [%0], %1, 0x989680;\n@!p bra WL;\n}" ::"r"(bar), "r"(parity) : "memory");
}
__device__ __forceinline__ void mbar_wait_cluster(uint32_t bar, uint32_t parity) {
    asm volatile("{\n.reg .pred p;\nWL:\nmbarrier.try_wait.parity.acquire.cluster.shared::cta.b64 p, [%0], %1, 0x989680;\n@!p bra WL;\n}" ::"r"(bar), "r"(parity) : "memory");
}
__device__ __forceinline__ void warp_arrive(uint32_t bar) {
    __syncwarp();
    asm volatile("{\n.reg .pred p;\nelect.sync _|p, 0xffffffff;\n@p mbarrier.arrive.shared::cta.b64 _, [%0];\n}" ::"r"(bar) : "memory");
}
__device__ __forceinline__ int opaque(int v) { return __shfl_sync(~0u, v, 0); }
__device__ __forceinline__ int fresh_tid() { int v; asm volatile("mov.u32 %0, %%tid.x;" : "=r"(v)); return v; }
__device__ __forceinline__ void bar_sync(int id, int n) { asm volatile("bar.sync %0, %1;" ::"r"(id), "r"(n) : "memory"); }
__device__ __forceinline__ void bar_arrive(int id, int n) { asm volatile("bar.arrive %0, %1;" ::"r"(id), "r"(n) : "memory"); }
__device__ __forceinline__ void fence_async_smem() { asm volatile("fence.proxy.async.shared::cta;" ::: "memory"); }
__device__ __forceinline__ void fence_async_global() { asm volatile("fence.proxy.async.global;" ::: "memory"); }
__device__ __forceinline__ void fence_gpu() { asm volatile("fence.release.gpu;" ::: "memory"); }
__device__ __forceinline__ void expect_e(uint32_t bar, uint32_t bytes) {
    asm volatile("{\n.reg .pred p;\nelect.sync _|p, 0xffffffff;\n@p mbarrier.arrive.expect_tx.shared::cta.b64 _, [%0], %1;\n}" ::"r"(bar), "r"(bytes) : "memory");
}
__device__ __forceinline__ void tma3_e(uint32_t dst, const CUtensorMap* m, int c0, int c1, int c2, uint32_t bar) {
    asm volatile("{\n.reg .pred p;\nelect.sync _|p, 0xffffffff;\n@p cp.async.bulk.tensor.3d.shared::cluster.global.mbarrier::complete_tx::bytes [%0], [%1, {%3, %4, %5}], [%2];\n}"
                 ::"r"(dst), "l"(m), "r"(bar), "r"(c0), "r"(c1), "r"(c2) : "memory");
}
__device__ __forceinline__ void bulk_e(uint32_t dst, const void* src, uint32_t bytes, uint32_t bar) {
    asm volatile("{\n.reg .pred p;\nelect.sync _|p, 0xffffffff;\n@p cp.async.bulk.shared::cluster.global.mbarrier::complete_tx::bytes [%0], [%1], %2, [%3];\n}"
                 ::"r"(dst), "l"(src), "r"(bytes), "r"(bar) : "memory");
}
__device__ __forceinline__ void init_e(uint32_t bar, int cnt) {
    asm volatile("{\n.reg .pred p;\nelect.sync _|p, 0xffffffff;\n@p mbarrier.init.shared::cta.b64 [%0], %1;\n}" ::"r"(bar), "r"(cnt) : "memory");
}
__device__ __forceinline__ void l2_prefetch_e(const void* src, uint32_t bytes) {
    asm volatile("{\n.reg .pred p;\nelect.sync _|p, 0xffffffff;\n@p cp.async.bulk.prefetch.L2.global [%0], %1;\n}" ::"l"(src), "r"(bytes) : "memory");
}
__device__ __forceinline__ uint32_t ld_relaxed(const uint32_t* p) { uint32_t v; asm volatile("ld.relaxed.gpu.global.u32 %0, [%1];" : "=r"(v) : "l"(p) : "memory"); return v; }
__device__ __forceinline__ void st_relaxed(uint32_t* p, uint32_t v) { asm volatile("st.relaxed.gpu.global.u32 [%0], %1;" ::"l"(p), "r"(v) : "memory"); }
__device__ __forceinline__ uint4 ld_relaxed4(const uint4* p) { uint4 v; asm volatile("ld.relaxed.gpu.global.v4.u32 {%0,%1,%2,%3}, [%4];" : "=r"(v.x), "=r"(v.y), "=r"(v.z), "=r"(v.w) : "l"(p) : "memory"); return v; }
__device__ __forceinline__ uint4 lds4(uint32_t a) { uint4 v; asm volatile("ld.shared.v4.u32 {%0,%1,%2,%3}, [%4];" : "=r"(v.x), "=r"(v.y), "=r"(v.z), "=r"(v.w) : "r"(a) : "memory"); return v; }
__device__ __forceinline__ float2 lds2f(uint32_t a) { float2 v; asm volatile("ld.shared.v2.f32 {%0,%1}, [%2];" : "=f"(v.x), "=f"(v.y) : "r"(a) : "memory"); return v; }
__device__ __forceinline__ uint32_t lds1(uint32_t a) { uint32_t v; asm volatile("ld.shared.u32 %0, [%1];" : "=r"(v) : "r"(a) : "memory"); return v; }
__device__ __forceinline__ void sts4(uint32_t a, uint4 v) { asm volatile("st.shared.v4.u32 [%0], {%1,%2,%3,%4};" ::"r"(a), "r"(v.x), "r"(v.y), "r"(v.z), "r"(v.w) : "memory"); }
__device__ __forceinline__ void sts1(uint32_t a, uint32_t v) { asm volatile("st.shared.u32 [%0], %1;" ::"r"(a), "r"(v) : "memory"); }
__device__ __forceinline__ void stsm4(uint32_t a, uint32_t r0, uint32_t r1, uint32_t r2, uint32_t r3) {
    asm volatile("stmatrix.sync.aligned.m8n8.x4.shared.b16 [%0], {%1,%2,%3,%4};" ::"r"(a), "r"(r0), "r"(r1), "r"(r2), "r"(r3));
}
__device__ __forceinline__ uint32_t pack2(float lo, float hi) { uint32_t r; asm("cvt.rn.bf16x2.f32 %0, %1, %2;" : "=r"(r) : "f"(hi), "f"(lo)); return r; }
__device__ __forceinline__ uint32_t pack2_relu(float lo, float hi) { uint32_t r; asm("cvt.rn.relu.bf16x2.f32 %0, %1, %2;" : "=r"(r) : "f"(hi), "f"(lo)); return r; }
__device__ __forceinline__ uint32_t hfma2(uint32_t a, uint32_t b, uint32_t c) { uint32_t r; asm("fma.rn.bf16x2 %0, %1, %2, %3;" : "=r"(r) : "r"(a), "r"(b), "r"(c)); return r; }
__device__ __forceinline__ uint32_t hmul2(uint32_t a, uint32_t b) { uint32_t r; asm("mul.rn.bf16x2 %0, %1, %2;" : "=r"(r) : "r"(a), "r"(b)); return r; }
__device__ __forceinline__ float bf_lo(uint32_t v) { return __uint_as_float(v << 16); }
__device__ __forceinline__ float bf_hi(uint32_t v) { return __uint_as_float(v & 0xFFFF0000u); }
__device__ __forceinline__ float bf_round(float v) { return bf_lo(pack2(v, 0.f)); }
__device__ __forceinline__ float ex2(float x) { float r; asm("ex2.approx.ftz.f32 %0, %1;" : "=f"(r) : "f"(x)); return r; }
__device__ __forceinline__ void mma16816(float* d, uint32_t a0, uint32_t a1, uint32_t a2, uint32_t a3, uint32_t b0, uint32_t b1) {
    asm("mma.sync.aligned.m16n8k16.row.col.f32.bf16.bf16.f32 {%0,%1,%2,%3}, {%4,%5,%6,%7}, {%8,%9}, {%0,%1,%2,%3};"
        : "+f"(d[0]), "+f"(d[1]), "+f"(d[2]), "+f"(d[3]) : "r"(a0), "r"(a1), "r"(a2), "r"(a3), "r"(b0), "r"(b1));
}
__device__ __forceinline__ void mma1688(float* d, uint32_t a0, uint32_t a1, uint32_t b0) {
    asm("mma.sync.aligned.m16n8k8.row.col.f32.bf16.bf16.f32 {%0,%1,%2,%3}, {%4,%5}, {%6}, {%0,%1,%2,%3};"
        : "+f"(d[0]), "+f"(d[1]), "+f"(d[2]), "+f"(d[3]) : "r"(a0), "r"(a1), "r"(b0));
}
__device__ __forceinline__ void ldsm4(uint32_t a, uint32_t* r) {
    asm volatile("ldmatrix.sync.aligned.m8n8.x4.shared.b16 {%0,%1,%2,%3}, [%4];" : "=r"(r[0]), "=r"(r[1]), "=r"(r[2]), "=r"(r[3]) : "r"(a));
}
__device__ __forceinline__ void ldsm4t(uint32_t a, uint32_t* r) {
    asm volatile("ldmatrix.sync.aligned.m8n8.x4.trans.shared.b16 {%0,%1,%2,%3}, [%4];" : "=r"(r[0]), "=r"(r[1]), "=r"(r[2]), "=r"(r[3]) : "r"(a));
}
__device__ __forceinline__ uint32_t nz(uint32_t v) { uint32_t r; asm("max.u32 %0, %1, 1;" : "=r"(r) : "r"(v)); return r; }
__device__ __forceinline__ float rcp(float x) { float r; asm("rcp.approx.ftz.f32 %0, %1;" : "=f"(r) : "f"(x)); return r; }
__device__ __forceinline__ uint2 ld_relaxed2(const void* p) { uint2 v; asm volatile("ld.relaxed.gpu.global.v2.u32 {%0,%1}, [%2];" : "=r"(v.x), "=r"(v.y) : "l"(p) : "memory"); return v; }
__host__ __device__ constexpr uint64_t dconst(uint32_t lbo, uint32_t sbo, uint32_t swz) {
    return ((uint64_t)(lbo >> 4) << 16) | ((uint64_t)(sbo >> 4) << 32) | ((uint64_t)swz << 62);
}
__device__ __forceinline__ uint32_t mkdesc(uint32_t addr, uint64_t c) { return (uint32_t)c | ((addr & 0x3FFFF) >> 4); }
#define WG_FENCE() asm volatile("wgmma.fence.sync.aligned;" ::: "memory")
#define WG_COMMIT() asm volatile("wgmma.commit_group.sync.aligned;" ::: "memory")
#define WG_WAIT(n) asm volatile("wgmma.wait_group.sync.aligned %0;" ::"n"(n) : "memory")
template <int N> __device__ __forceinline__ void reg_fence(float* d) {
#pragma unroll
    for (int i = 0; i < N; i++) asm volatile("" : "+f"(d[i])::"memory");
}
template <int N> __device__ __forceinline__ void reg_def(float* d) {
#pragma unroll
    for (int i = 0; i < N; i++) asm volatile("" : "=f"(d[i]));
}
template <int N> __device__ __forceinline__ void reg_def(uint32_t* d) {
#pragma unroll
    for (int i = 0; i < N; i++) asm volatile("" : "=r"(d[i]));
}
__device__ __forceinline__ void wait_flags(const uint32_t* p, uint32_t target, uint32_t mask) {
    int n = 0;
    while (~__ballot_sync(~0u, ld_relaxed(p) == target) & mask) { if (++n > SPIN_LIMIT) __trap(); }
    asm volatile("fence.acquire.gpu;" ::: "memory");
}
__device__ __forceinline__ float silu_bf(uint32_t cbits) {
    const float c = __uint_as_float(cbits << 16);
    return bf_round(__fdividef(c, 1.f + fminf(ex2(-1.4426950408889634f * c), 1e30f)));
}
__device__ __forceinline__ void gemv_part(uint32_t wmbuf, int wp, int lane) {
    const uint32_t wa = wmbuf + wp * 512 + (8 * (lane >> 4) + (lane & 7)) * 32 + ((lane >> 3) & 1) * 16;
    float d[4] = {};
#pragma unroll
    for (int i = 0; i < 4; i++) {
        uint32_t A[4];
        const float2 v = lds2f(wmbuf + 28672 + (wp + 8 * i) * 32 + (lane & 3) * 8);
        ldsm4t(wa + (i < 3 || wp < 4 ? i : 0) * 4096, A);
        mma16816(d, A[0], A[1], A[2], A[3], __float_as_uint(v.x), __float_as_uint(v.y));
    }
    if ((lane & 3) == 0) {
        sts1(wmbuf + 29696 + (wp * 16 + (lane >> 2)) * 4, __float_as_uint(d[0]));
        sts1(wmbuf + 29696 + (wp * 16 + 8 + (lane >> 2)) * 4, __float_as_uint(d[2]));
    }
}
__device__ __forceinline__ uint32_t mod_word(float v, int col, uint32_t target) {
    v = bf_round(v);
    if ((col >= DM && col < 2 * DM) || (col >= 4 * DM && col < 5 * DM)) v += 1.f;
    return (pack2(v, 0.f) << 16) | (target & 0xFFFFu);
}
__device__ __forceinline__ const uint4* mod_src(int i, int r, int j, bool p2) {
    i = min(i, p2 ? 251 : 223);
    return (const uint4*)g_mod + (r & 7) * (6 * DM / 4) + (i < 224 ? (p2 ? 336 : 0) + i : (i < 238 ? 14 * j + i : 14 * j + i + 322));
}
__device__ __forceinline__ void mod_store(uint32_t sb, uint4 v, const uint4* src, int i) {
    const uint32_t tag = lds1(sb + M_EPOCH) + 1;
    while (__any_sync(~0u, (((v.x ^ tag) | (v.y ^ tag) | (v.z ^ tag) | (v.w ^ tag)) & 0xFFFFu) != 0u)) v = ld_relaxed4(src);
    if (i < 224) {
        const int isc = i >= 112, c4 = i - 112 * isc;
        const uint32_t a = sb + M_ST + (c4 >> 2) * 64 + (c4 & 1) * 32 + (c4 & 2) * 4 + (isc ? 0 : 4);
        sts1(a, __byte_perm(v.x, v.y, 0x7632));
        sts1(a + 16, __byte_perm(v.z, v.w, 0x7632));
    } else if (i < 252) {
        sts4(sb + M_G + (i - 224) * 16, make_uint4(v.x & 0xFFFF0000u, v.y & 0xFFFF0000u, v.z & 0xFFFF0000u, v.w & 0xFFFF0000u));
    }
}
__device__ __forceinline__ int pass_f(int fs, int ps) { return 224 * fs + ((fs & 1) ? (ps == 0 ? 96 : ps == 1 ? 32 : 0) : (ps == 0 ? 0 : ps == 1 ? 128 : 192)); }
__device__ __forceinline__ constexpr uint32_t slot_off(int l) { return l * 16384 + (l >= 10 ? 8192 : 0); }
constexpr uint64_t RING_ORDER = 0x6543C92B81A70ull;
constexpr uint32_t Y_XCH = 49152;
__device__ __forceinline__ constexpr int g1_slot(int s) { return s % 7; }
__device__ __noinline__ void x1_fix(const uint32_t* g, uint32_t sa, int s) {
#pragma unroll 1
    for (int k = 4 * s; k < 4 * s + 4;) {
        const uint4 v = ld_relaxed4((const uint4*)(g + k * 256));
        sts4(sa + k * 1024, v);
        k += 2 * __all_sync(~0u, min(min(v.x, v.y), min(v.z, v.w)) != 0u);
    }
    __syncwarp();
}
struct LnRow { uint32_t nm, rs; };
__device__ __forceinline__ LnRow ln_coeffs(float mean, float msq) {
    const float var = bf_round(fmaxf(msq - mean * mean, 0.f));
    float sd;
    asm("sqrt.approx.f32 %0, %1;" : "=f"(sd) : "f"(bf_round(var + 1e-5f)));
    const float rs = bf_round(rcp(bf_round(sd))), nm = -bf_round(mean) * rs;
    return LnRow{pack2(nm, nm), pack2(rs, rs)};
}
__device__ __forceinline__ uint32_t ln_norm(uint32_t x, const LnRow& c) { return hfma2(x, c.rs, c.nm); }
__device__ __forceinline__ uint32_t ln_mod(uint32_t y, uint32_t sc, uint32_t sh) { return hfma2(y, sc, sh); }

#define LOADW bulk_e(dst, g_wd + (size_t)((f >> 5) * 4 + nq) * 1792, 7168, bar);
template <int sec> __device__ __forceinline__ void ring_loader(const Params& p, uint32_t sb_, int r_, int j_, int lane) {
    const uint32_t sb = opaque(sb_);
    const int r = opaque(r_), j = opaque(j_), nq = j >> 1, fs = 4 * (j & 1) + nq;
    const int fa = pass_f(fs, 0), fb = pass_f(fs, 1), fc = pass_f(fs, 2);
    const uint32_t* h2src = (const uint32_t*)__shfl_sync(~0u, (unsigned long long)(p.actb + (size_t)r * RB_WORDS + RB_H2), 0);
    const CUtensorMap* gmap = (const CUtensorMap*)__shfl_sync(~0u, (unsigned long long)(&p.ga + sec), 0);
#define BAR(i) (sb + M_BAR + 8 * (i))
#define kh (j & 1)
            int sl = 0;
#pragma unroll 1
            for (int s = 0; s < 21; s++) {
                if (s == 7) { wait_flags(g_flag + (8 * r + j) * 192 + 96 + lane, lds1(sb + M_EPOCH) + 1, 0xFFFFu); fence_async_global(); }
                if (s >= 1 && s < 3) mbar_wait(BAR(B_FULL + s - 1), 0);
                mbar_wait(BAR(B_EMPTY + sl), s >= 7 && s < 14);
                expect_e(BAR(B_FULL + sl), 8192);
                tma3_e(sb + slot_off(sl) + sec * 8192, gmap + (s < 14 ? 0 : 2), 0, s < 14 ? 32 * s : 64 * sl, (s < 14 ? fa : fb) >> 6, BAR(B_FULL + sl));
                sl = sl == 6 ? 0 : sl + 1;
            }
#pragma unroll 1
            for (int s = 0; s < 7; s++) {
                const uint32_t bar = BAR(B_FULL + s);
                uint32_t dst = sb + slot_off(s) + sec * 4096;
                mbar_wait(BAR(B_EMPTY + s), 1);
                expect_e(bar, s < 3 ? 8192 : s > 3 ? 7168 : sec ? 4096 : 4096 + 7168);
                if (s < 4) tma3_e(dst, gmap + 4, 0, 128 * s, fc >> 5, bar);
                if (s < 3) tma3_e(dst + 8192, gmap + 4, 0, 128 * s + 64, fc >> 5, bar);
                else if (s > 3 || !sec) {
                    const int f = s == 3 ? fc : (s < 6 ? fa + 64 * (s - 4) : fb) + 32 * sec;
                    dst = sb + slot_off(s) + (s == 3 || sec ? 8192 : 0);
                    LOADW
                }
            }
            if (!sec) PROFH(3);
            if (sec) asm volatile("prefetch.tensormap [%0];" ::"l"(&p.om) : "memory");
            int e = 0;
#pragma unroll 1
            for (int grp = 0; grp < 9; grp++) {
                const int ps = grp >= 6 ? 2 : grp >= 3 ? 1 : 0;
                int sidx = grp - 3 * ps;
                if (sec && sidx == 0) { mbar_wait(BAR(B_HRDY + ps), 0); fence_async_global(); }
                sidx += sidx >= nq;
                int f = pass_f(4 * kh + sidx, ps);
#pragma unroll 1
                for (int k = 4 >> ps; k > 0; k--, e++, f += 32) {
                    sl = (RING_ORDER >> (4 * (e < 13 ? e : e - 13))) & 15;
                    const uint32_t dst = sb + slot_off(sl), bar = BAR(B_FULL + sl);
                    mbar_wait(BAR(B_EMPTY + sl), e >= 13);
                    if (e >= WIN) mbar_wait(BAR(B_FULL + ((RING_ORDER >> (4 * (e - WIN < 13 ? e - WIN : e - WIN - 13))) & 15)), e - WIN >= 13);
                    expect_e(bar, sec ? 8192 : 7168);
                    if (!sec) { LOADW }
                    else bulk_e(dst + 8192, h2src + f * 64, 8192, bar);
                }
            }
            if (!sec) PROFH(4);
}

#define PROF_PARAMS
#define PROF_ARGS
__device__ __noinline__ void helper_late(const Params& p, int r_, int j_, int warp_ PROF_PARAMS) {
    extern __shared__ __align__(1024) unsigned char smem[];
    const uint32_t sb = (uint32_t)__cvta_generic_to_shared(smem);
    const int r = opaque(r_), j = opaque(j_), warp = opaque(warp_), nq = j >> 1, b = 8 * r + j;
    uint32_t* const act = (uint32_t*)__shfl_sync(~0u, (unsigned long long)(p.actb + (size_t)r * RB_WORDS), 0);
    {
        const int lane = fresh_tid() & 31;
        const uint32_t target = lds1(sb + M_EPOCH) + 1;
        if (warp == 8) { expect_e(BAR(B_XCH), 7168); expect_e(BAR(B_XCH + 1), 7168); }
            if (warp == 9) {
#pragma unroll 1
                for (int kv = 0; kv < 2; kv++) {
                    mbar_wait(BAR(B_PUB + kv), 0);
                    wait_flags(g_flag + b * 192 + lane, target, (r >= 2 ? 6u : r == 1 ? 2u : 0u) << (8 * kv));
                    fence_async_global();
                    const uint32_t dst = sb + OFF_Y + (kv ? Y_VR : Y_K);
                    expect_e(BAR(B_KRFULL + kv), r >= 2 ? 28672 : r == 1 ? 14336 : 0);
                    if (r >= 2) bulk_e(dst, act - 2 * RB_WORDS + RB_KV + j * 7168 + kv * 3584, 14336, BAR(B_KRFULL + kv));
                    if (r >= 1) bulk_e(dst + 14336, act - RB_WORDS + RB_KV + j * 7168 + kv * 3584, 14336, BAR(B_KRFULL + kv));
                }
            } else if (warp == 8) {
#pragma unroll 1
                for (int it = 0; it < 2; it++) {
                    const int i0 = lane + 128 * it;
                    uint4 v[4];
#pragma unroll
                    for (int k = 0; k < 4; k++) v[k] = ld_relaxed4(mod_src(i0 + 32 * k, r, j, true));
#pragma unroll
                    for (int k = 0; k < 4; k++) mod_store(sb, v[k], mod_src(i0 + 32 * k, r, j, true), i0 + 32 * k);
                }
                warp_arrive(BAR(B_MOD1));
            } else if (warp == 11) {
                if (kh == 1 && r < 14) {
                    const uint32_t wmbuf = sb + OFF_X + HALF;
                    const int mcol = 2 * DM + 32 * (4 * r + nq);
                    uint32_t cb[7];
#pragma unroll
                    for (int i = 0; i < 7; i++) cb[i] = __ldg((const uint32_t*)p.c + lane + 32 * i);
#pragma unroll
                    for (int i = 0; i < 7; i++) cb[i] = pack2(silu_bf(cb[i] & 0xFFFFu), silu_bf(cb[i] >> 16));
                    mbar_wait(BAR(B_XFREE), 0);
                    tma3_e(wmbuf, &p.wm2, mcol, 0, 0, BAR(B_WMFULL));
                    tma3_e(wmbuf + 14336, &p.wm2, mcol, 224, 0, BAR(B_WMFULL));
#pragma unroll
                    for (int i = 0; i < 7; i++) sts1(wmbuf + 28672 + (lane + 32 * i) * 4, cb[i]);
                    __syncwarp();
                    mbar_wait(BAR(B_WMFULL), 0);
                    float a[8] = {};
#pragma unroll 2
                    for (int i = 0; i < 28; i++) {
                        const int rp = (lane >> 2) + 8 * i;
                        const uint32_t sv = lds1(wmbuf + 28672 + rp * 4);
                        const uint4 u = lds4(wmbuf + rp * 128 + (lane & 3) * 16 + (lane & 4) * 16), v = lds4(wmbuf + rp * 128 + (lane & 3) * 16 + 64 - (lane & 4) * 16);
                        const float s0 = (lane & 4) ? bf_hi(sv) : bf_lo(sv), s1 = (lane & 4) ? bf_lo(sv) : bf_hi(sv);
                        a[0] += s0 * bf_lo(u.x) + s1 * bf_lo(v.x); a[1] += s0 * bf_hi(u.x) + s1 * bf_hi(v.x);
                        a[2] += s0 * bf_lo(u.y) + s1 * bf_lo(v.y); a[3] += s0 * bf_hi(u.y) + s1 * bf_hi(v.y);
                        a[4] += s0 * bf_lo(u.z) + s1 * bf_lo(v.z); a[5] += s0 * bf_hi(u.z) + s1 * bf_hi(v.z);
                        a[6] += s0 * bf_lo(u.w) + s1 * bf_lo(v.w); a[7] += s0 * bf_hi(u.w) + s1 * bf_hi(v.w);
                    }
#pragma unroll
                    for (int i = 0; i < 4; i++) { const bool hh = lane & 16; a[i] = (hh ? a[i + 4] : a[i]) + __shfl_xor_sync(~0u, hh ? a[i] : a[i + 4], 16); }
#pragma unroll
                    for (int i = 0; i < 2; i++) { const bool hh = lane & 8; a[i] = (hh ? a[i + 2] : a[i]) + __shfl_xor_sync(~0u, hh ? a[i] : a[i + 2], 8); }
                    const float sum = ((lane & 4) ? a[1] : a[0]) + __shfl_xor_sync(~0u, (lane & 4) ? a[0] : a[1], 4);
                    const int col = mcol + 8 * (lane & 3) + (lane >> 2);
                    const uint32_t word = mod_word(sum, col, target);
#pragma unroll
                    for (int i = 0; i < 8; i++) st_relaxed(g_mod + i * 6 * DM + col, word);
                }
                warp_arrive(BAR(B_WMFREE));
                mbar_wait(BAR(B_VRFULL), 0);
#pragma unroll 1
                for (int k = 0; k < (r < 12 ? 2 : 1); k++) {
                    const int u = 28 * kh + r + 16 * k;
                    expect_e(BAR(B_XFULL + k), 7168);
                    tma3_e(sb + OFF_Y + Y_CELL, &p.dn, 0, 32 * u, 7 * j, BAR(B_XFULL + k));
                    tma3_e(sb + OFF_Y + Y_CELL + 3584, &p.dn, 0, 32 * u, 7 * (j ^ 1), BAR(B_XFULL + k));
                    mbar_wait(BAR(B_XFULL + k), 1);
                    asm volatile("{\n.reg .pred p;\nelect.sync _|p, 0xffffffff;\n@p cp.async.bulk.global.shared::cta.bulk_group [%0], [%1], 7168;\n"
                                 "cp.async.bulk.commit_group;\ncp.async.bulk.wait_group.read 0;\n}" ::"l"(g_wd + (size_t)(u * 4 + nq) * 1792), "r"(sb + OFF_Y + Y_CELL) : "memory");
                    __syncwarp();
                }
                warp_arrive(BAR(B_FULLK));
                asm volatile("cp.async.bulk.wait_group 0;" ::: "memory");
                __syncwarp();
                fence_gpu();
                if (lane < 16) st_relaxed(g_flag + (8 * lane + j) * 192 + 96 + r, target);
            }
        if (warp == 8 || warp == 11) {
            const int sec = warp == 11;
            if (sec) ring_loader<1>(p, sb, r, j, lane); else ring_loader<0>(p, sb, r, j, lane);
            mbar_wait(BAR(B_DONE), 0);
        } else if (warp == 9) {
#pragma unroll
            for (int ev = 0; ev < 4; ev++) { expect_e(BAR(B_GFULL + ev), ev < 2 ? HALF / 2 : 16384); expect_e(BAR(B_XFULL + 2 + ev), ev < 2 ? HALF / 2 : HALF - 16384); }
            mbar_wait(BAR(B_PUB + 2), 0);
            expect_e(BAR(B_KRFULL), 14336);
            tma3_e(sb + OFF_Y + Y_K, &p.xr, 56 * j, 128 * r, 0, BAR(B_KRFULL));
            tma3_e(sb + OFF_Y + Y_Q, &p.xr, 56 * j, 128 * r + 64, 0, BAR(B_KRFULL));
            const int par = (target - 1) & 1;
#pragma unroll 1
            for (int ev = 0; ev < 4; ev++) {
                if (ev == 1) { mbar_wait(BAR(B_FULLK), 1); mbar_wait(BAR(B_XFREE), 1); }
                const int tile = (ev & 1) + (ev >> 1) * par * 2;
                const uint32_t dst = sb + (ev == 0 ? OFF_X : OFF_Y + (ev & 1) * HALF), first = ev < 2 ? HALF / 2 : 16384;
                const char* src = (const char*)(act + RB_O + ((ev >> 1) * 2 + tile) * 14336);
                wait_flags(g_flag + b * 192 + (ev < 2 ? 32 : 64 + 32 * ev) + lane, target, ev < 2 ? 0xFFu << (8 * ev) : ~0u);
                if (ev >= 2) warp_arrive(BAR(B_FULLV + (ev & 1)));
                fence_async_global();
                bulk_e(dst, src, first, BAR(B_GFULL + ev));
                bulk_e(dst + first, src + first, HALF - first, BAR(B_XFULL + 2 + ev));
                if (ev) PROFH(4 + ev);
            }
            mbar_wait(BAR(B_XFULL + 5), 1);
#pragma unroll 1
            for (int hf = 0; hf < 2; hf++) {
                const int tile = (par ^ 1) * 2 + hf;
                uint4* xz = (uint4*)(act + RB_X1 + tile * 14336 + j * 1792) + lane;
#pragma unroll
                for (int i = 0; i < 14; i++) xz[i * 32] = make_uint4(0, 0, 0, 0);
                ((uint4*)(act + RB_ST + (tile * 8 + j) * 128))[lane] = make_uint4(0, 0, 0, 0);
            }
#pragma unroll 1
            for (int ps = 0; ps < 3; ps++) {
                mbar_wait(BAR(B_PUB + 6 + ps), 0);
                if (ps == 1) {
                    fence_gpu();
                    if (lane < 8) st_relaxed(g_flag + (8 * r + lane) * 192 + 72 + j, target);
                }
                wait_flags(g_flag + b * 192 + 64 + lane, target, (0x55u << kh) << (8 * ps));
                warp_arrive(BAR(B_HRDY + ps));
                PROFH(9 + ps);
            }
        } else {
#pragma unroll 1
            for (int k = 0; k < 9; k++) {
                if (k == 4 || k == 5 || k == 7) continue;
                uint32_t* fp = k < 2 ? g_flag + (b + 8 * lane) * 192 + k * 8 + lane : g_flag + (8 * r + lane) * 192 + 16 + k * 8 + j;
                mbar_wait(BAR(B_PUB + k), 0);
                fence_gpu();
                if (k < 2 ? (lane == 1 || lane == 2) : lane < 8) st_relaxed(fp, target);
                if (k == 0) l2_prefetch_e((const char*)p.wd + (size_t)b * 12544, 12544);
                if (k == 1) {
                    mbar_wait(BAR(B_VRFULL), 0);
                    l2_prefetch_e((const char*)p.wg + (size_t)b * 12544, 12544);
                    l2_prefetch_e((const char*)p.wu + (size_t)b * 12544, 12544);
                }
                if (k >= 3 && k <= 5) PROFH(k - 3);
            }
        }
    }
}

__global__ void __cluster_dims__(2, 1, 1) __launch_bounds__(384, 1) fused_block_kernel(const __grid_constant__ Params p) {
    extern __shared__ __align__(1024) unsigned char smem[];
    const uint32_t sb = (uint32_t)__cvta_generic_to_shared(smem);
    const int tid = threadIdx.x, lane = tid & 31, warp = __shfl_sync(~0u, tid >> 5, 0);
    const int m = blockIdx.x >> 1;
    int r, nq;
    if (m < 4) { r = 15; nq = m; }
    else if (m < 36) { r = (m - 4) & 7; nq = (m - 4) >> 3; }
    else { nq = (m - 36) / 7; r = m - 28 - 7 * nq; }
    const int j = opaque(2 * nq + (blockIdx.x & 1)), b = 8 * r + j, fs = 4 * kh + nq;
#define act (p.actb + (size_t)r * RB_WORDS)
    uint32_t ticket = 0;
    if (tid == 288) ticket = atomicAdd(&g_ticket, 1u);
    if (warp == 10 && blockIdx.x < 112) {
#pragma unroll
        for (int i = 0; i < 4; i++) l2_prefetch_e(p.wmod + (size_t)(4 * blockIdx.x + i) * (6 * DM), 4 * DM);
    }
    if (warp == 11) l2_prefetch_e((const char*)p.x + (size_t)blockIdx.x * 14336, 14336);
    if (lane == 0 && warp < 9 && warp != 6 && warp != 7) {
        const int i0 = warp == 8 ? 0 : 8 + 8 * warp, cnt = warp == 0 || warp == 8 ? 1 : warp < 3 ? 2 : 8;
#pragma unroll
        for (int k = 0; k < 8; k++) if (i0 + k != B_WMFULL) mbar_init(BAR(i0 + k), cnt);
        if (warp == 8) mbar_init(BAR(B_WMFULL), 1);
        asm volatile("fence.mbarrier_init.release.cluster;" ::: "memory");
        fence_async_smem();
    }

    if (warp >= 8) {
        const int lane = fresh_tid() & 31;
        const bool early = kh == 0, gemv = r < 14;
        const int mcol = early ? 16 * (4 * r + nq) : 2 * DM + 32 * (4 * r + nq);
        const uint32_t wmbuf = sb + OFF_Y + HALF;
        if (warp == 8) {
            __syncwarp();
            expect_e(BAR(B_WMFULL), gemv ? 28672 >> early : 0);
            if (early && gemv) { tma3_e(wmbuf, &p.wm, mcol, 0, 0, BAR(B_WMFULL)); tma3_e(wmbuf + 7168, &p.wm, mcol, 224, 0, BAR(B_WMFULL)); }
#pragma unroll
            for (int kb = 0; kb < 7; kb++) {
                expect_e(BAR(B_XFULL + kb), 16384);
                tma3_e(sb + OFF_X + kb * 16384, &p.xm, 64 * kb, 128 * r, 0, BAR(B_XFULL + kb));
            }
        }
        asm volatile("setmaxnreg.dec.sync.aligned.u32 56;");
        if (warp == 10) {
#pragma unroll
            for (int i = 56; i < 64; i++) init_e(BAR(i), 1);
            fence_async_smem();
        }
        bar_arrive(0, 384);
        asm volatile("barrier.cluster.arrive.relaxed.aligned;" ::: "memory");
        if (warp == 8) {
            mbar_wait(BAR(B_XFULL), 0);
            l2_prefetch_e((const char*)p.wqkv + (size_t)b * 9408, 9408);
#pragma unroll 1
            for (int mt = 0; mt < 4; mt++) {
                if (mt == 1) bar_sync(9, 384);
                if (mt == 3) mbar_wait(BAR(B_WMFREE), 0);
                if (mt == 1 && early) mbar_wait(BAR(B_WMFREE), 0);
                if (mt) mbar_wait(BAR(mt == 1 ? B_FULLK : mt == 2 ? B_MOD1 : B_VRFULL), 0);
                const uint32_t bar = BAR(mt == 3 ? B_WOFULL : B_FULLK + mt), dst = sb + (mt < 2 ? OFF_Y : OFF_X) + (mt & 1) * HALF;
                const int c0 = (mt < 2 ? DM + DM * mt : 0) + 56 * j - 8 * kh;
                expect_e(bar, HALF);
                tma3_e(dst, mt == 3 ? &p.wo : &p.qkv, c0, 0, 0, bar);
                tma3_e(dst + HALF / 2, mt == 3 ? &p.wo : &p.qkv, c0, 224, 0, bar);
            }
        } else {
            if (warp == 10 && lane < 14) asm volatile("prefetch.tensormap [%0];" ::"l"(&p.wm + lane) : "memory");
            if (tid == 288) sts1(sb + M_EPOCH, ticket / NCTA);
            bar_sync(9, 384);
            if (warp == 9 && lane < 8) mbar_arrive(BAR(B_EPOCH));
            if (warp == 11 && early) {
                const uint32_t target = lds1(sb + M_EPOCH) + 1;
                mbar_wait(BAR(B_GEMV), 0);
                float sum = 0.f;
#pragma unroll
                for (int i = 0; i < 8; i++) sum += *(const float*)(smem + OFF_Y + HALF + 29696 + (i * 16 + (lane & 15)) * 4);
                uint32_t* mg = g_mod + mcol + (lane & 15) + (lane >> 4) * 4 * 6 * DM;
                const uint32_t word = mod_word(sum, mcol, target);
                if (gemv) { st_relaxed(mg, word); st_relaxed(mg + 6 * DM, word); st_relaxed(mg + 12 * DM, word); st_relaxed(mg + 18 * DM, word); }
            }
        }
    }
    if (warp < 8) {
        const int w = (warp >> 2) ^ 1, wi = warp & 3;
#define COORDS const int t = fresh_tid() & 127, lane = t & 31, q = lane & 3, lr = lane >> 2, ra = 64 * w + 16 * wi + lr; \
        const uint32_t lx = (lane >> 4) ^ (lane & 7), mrow = (64 * w + 16 * wi + ((lane >> 3) & 1) * 8 + (lane & 7)) * 128; \
        (void)q; (void)lr; (void)ra; (void)lx; (void)mrow;
#define WAIT(i, par) mbar_wait_c(BAR(i), par)
        constexpr uint64_t DB128 = dconst(4096, 1024, 1);
        {
            const int wd = fresh_tid();
            const uint32_t cb = wd < 224 ? __ldg((const uint32_t*)p.c + wd) : 0u;
            sts1(sb + OFF_Y + HALF + 28672 + (wd >> 3) * 32 + (wd & 3) * 8 + (wd & 4), pack2(silu_bf(cb & 0xFFFFu), silu_bf(cb >> 16)));
        }
        bar_arrive(9, 384);
        bar_sync(0, 384);
        asm volatile("barrier.cluster.arrive.relaxed.aligned;" ::: "memory");
        asm volatile("setmaxnreg.inc.sync.aligned.u32 224;");
        PROFC(0);
        {
            COORDS
            uint32_t h[112];
            LnRow ca, cb;
            const int mi = min(128 * w + t, 223);
            const uint4* msrc = mod_src(mi, r, j, false);
            uint4 mv;
            {
                float ds[4] = {}, da[2][4] = {}, db[2][4] = {};
                const uint32_t ONE2 = 0x3F803F80u;
#pragma unroll
                for (int kb = 0; kb < 7; kb++) {
                    if (kb == 0 && kh == 0) { WAIT(B_WMFULL, 0); gemv_part(sb + OFF_Y + HALF, warp, lane); warp_arrive(BAR(B_GEMV)); }
                    WAIT(B_XFULL + kb, 0);
#pragma unroll
                    for (int k4 = 0; k4 < 4; k4++) ldsm4(sb + OFF_X + mrow + kb * 16384 + (((2 * k4) ^ lx) << 4), h + 16 * kb + 4 * k4);
#pragma unroll
                    for (int k4 = 0; k4 < 4; k4++) {
                        const uint32_t* f = h + 16 * kb + 4 * k4;
                        mma16816(ds, f[0], f[1], f[2], f[3], ONE2, ONE2);
                        mma1688(da[0], f[0], f[1], f[0]); mma1688(db[0], f[0], f[1], f[1]);
                        mma1688(da[1], f[2], f[3], f[2]); mma1688(db[1], f[2], f[3], f[3]);
                    }
                }
                mv = ld_relaxed4(msrc);
                warp_arrive(BAR(B_XFREE));
                float qa = (lr & 1) ? da[0][1] + da[1][1] : da[0][0] + da[1][0];
                float qb = (lr & 1) ? db[0][3] + db[1][3] : db[0][2] + db[1][2];
                const int src = (lane & ~3) | (lr >> 1);
                qa = __shfl_sync(~0u, qa, src);
                qb = __shfl_sync(~0u, qb, src);
                ca = ln_coeffs(ds[0] * (1.f / DM), qa * (1.f / DM));
                cb = ln_coeffs(ds[2] * (1.f / DM), qb * (1.f / DM));
#pragma unroll
                for (int i = 0; i < 4 * NPRE; i += 2) { h[i] = ln_norm(h[i], ca); h[i + 1] = ln_norm(h[i + 1], cb); }
            }
            PROFC(1);
            {
                float ak[28], av[28], aq[28];
                uint32_t kp[14], vp[14];
                const uint64_t bq0 = (DB128 & ~0xFFFFFFFFull) | (mkdesc(sb + OFF_X, DB128) + kh), bk0 = bq0 + (OFF_Y >> 4), bv0 = bk0 + (HALF >> 4);
                uint32_t* kvg = act + RB_KV + j * 7168 + (8 * w + 2 * wi) * 224 + lane;
                WAIT(B_EPOCH, 0);
                mod_store(sb, mv, msrc, mi);
                bar_sync(3, 256);
                if (warp == 0) warp_arrive(BAR(B_MOD1));
                WAIT(B_FULLK, 0);
                PROFC(2);
                reg_def<28>(ak);
#pragma unroll
                for (int g4 = 0; g4 < 5; g4++) {
                    const int k0 = g4 == 0 ? 0 : g4 == 1 ? 2 : 7 * g4 - 7, k1 = g4 == 0 ? 2 : 7 * g4;
#pragma unroll
                    for (int ks = k0; ks < k1; ks++) {
                        const uint4 st = *(const uint4*)(smem + M_ST + ks * 64 + q * 16);
                        if (ks >= NPRE) {
                            h[4 * ks] = ln_norm(h[4 * ks], ca); h[4 * ks + 1] = ln_norm(h[4 * ks + 1], cb);
                            h[4 * ks + 2] = ln_norm(h[4 * ks + 2], ca); h[4 * ks + 3] = ln_norm(h[4 * ks + 3], cb);
                        }
                        h[4 * ks] = ln_mod(h[4 * ks], st.x, st.y); h[4 * ks + 1] = ln_mod(h[4 * ks + 1], st.x, st.y);
                        h[4 * ks + 2] = ln_mod(h[4 * ks + 2], st.z, st.w); h[4 * ks + 3] = ln_mod(h[4 * ks + 3], st.z, st.w);
                    }
                    WG_FENCE();
#pragma unroll
                    for (int ks = k0; ks < k1; ks++) wgmma_rl_56(ak, h[4 * ks], h[4 * ks + 1], h[4 * ks + 2], h[4 * ks + 3], bk0 + ks * 128, ks != 0);
                }
                WG_COMMIT();
                PROFC(3);
                reg_def<28>(av);
                WG_WAIT(0);
                reg_fence<28>(ak);
#pragma unroll
                for (int g = 0; g < 7; g++) {
                    kp[2 * g] = pack2(ak[4 * g], ak[4 * g + 1]); kp[2 * g + 1] = pack2(ak[4 * g + 2], ak[4 * g + 3]);
                    kvg[g * 32] = kp[2 * g]; kvg[224 + g * 32] = kp[2 * g + 1];
                }
                warp_arrive(BAR(B_PUB));
                PROFC(4);
                WAIT(B_FULLV, 0);
                WG_FENCE();
#pragma unroll
                for (int ks = 0; ks < 28; ks++) wgmma_rl_56(av, h[4 * ks], h[4 * ks + 1], h[4 * ks + 2], h[4 * ks + 3], bv0 + ks * 128, ks != 0);
                WG_COMMIT();
                reg_def<28>(aq);
                WAIT(B_FULLQ, 0);
                WG_FENCE();
#pragma unroll
                for (int ks = 0; ks < VPRE; ks++) wgmma_rl_56(aq, h[4 * ks], h[4 * ks + 1], h[4 * ks + 2], h[4 * ks + 3], bq0 + ks * 128, ks != 0);
                WG_COMMIT();
                WG_WAIT(1);
                reg_fence<28>(av);
#pragma unroll
                for (int g = 0; g < 7; g++) {
                    vp[2 * g] = pack2(av[4 * g], av[4 * g + 1]); vp[2 * g + 1] = pack2(av[4 * g + 2], av[4 * g + 3]);
                    kvg[3584 + g * 32] = vp[2 * g]; kvg[3584 + 224 + g * 32] = vp[2 * g + 1];
                }
                warp_arrive(BAR(B_PUB + 1));
                PROFC(5);
                WG_FENCE();
#pragma unroll
                for (int ks = VPRE; ks < 28; ks++) wgmma_rl_56(aq, h[4 * ks], h[4 * ks + 1], h[4 * ks + 2], h[4 * ks + 3], bq0 + ks * 128, ks != 0);
                WG_COMMIT();
                WAIT(B_PUB + 1, 0);
                const uint32_t rg = 8 * w + 2 * wi + ((lane >> 3) & 1);
                const uint32_t ko = sb + OFF_Y + Y_KOWN + rg * 896 + (lane & 7) * 16, qo = sb + OFF_Y + Y_Q + rg * 1024 + (lane >> 4) * 128 + (lane & 7) * 16;
#pragma unroll
                for (int g = 0; g < 6; g += 2) {
                    stsm4(ko + (g + (lane >> 4)) * 128, kp[2 * g], kp[2 * g + 1], kp[2 * g + 2], kp[2 * g + 3]);
                    stsm4(ko + (Y_VOWN - Y_KOWN) + (g + (lane >> 4)) * 128, vp[2 * g], vp[2 * g + 1], vp[2 * g + 2], vp[2 * g + 3]);
                }
                stsm4(ko + (lane >> 4) * (Y_VOWN - Y_KOWN) + 6 * 128, kp[12], kp[13], vp[12], vp[13]);
                WG_WAIT(0);
                reg_fence<28>(aq);
                __syncwarp();
                if (lane < 3 && w == 1) mbar_arrive(BAR(B_EMPTY + lane));
                uint32_t qp[14];
#pragma unroll
                for (int i = 0; i < 14; i++) qp[i] = pack2(aq[2 * i], aq[2 * i + 1]);
                stsm4(qo, qp[0], qp[1], qp[2], qp[3]);
                stsm4(qo + 256, qp[4], qp[5], q < 2 ? qp[6] : 0u, q < 2 ? qp[7] : 0u);
                stsm4(qo + 512, q < 2 ? 0u : qp[6], q < 2 ? 0u : qp[7], qp[8], qp[9]);
                stsm4(qo + 768, qp[10], qp[11], qp[12], qp[13]);
                fence_async_smem();
                if (w == 0) { bar_arrive(4, 256); bar_sync(1, 128); } else { bar_arrive(5, 256); bar_sync(4, 256); }
            }
        }
        PROFC(6);
        WAIT(B_KRFULL, 0);
        PROFC(7);
        {
#pragma unroll 1
            for (int hf = 0; hf < 2; hf++) {
                COORDS
                if (hf > w) bar_sync(5, 256);
                float s[160];
                const float CS = 0.18898223650461361f * 1.4426950408889634f;
                const float NEG = __int_as_float(0xFF800000);
                constexpr uint64_t DQ = dconst(128, 1024, 0), DK = dconst(128, 896, 0);
                {
                    const uint32_t qd = mkdesc(sb + OFF_Y + Y_Q + hf * 8192 + w * 512, DQ), kd = mkdesc(sb + OFF_Y + Y_K + hf * 8 * 896 + w * 384, DK);
                    reg_def<160>(s);
                    if (r < 2) {
#pragma unroll
                        for (int i = 0; i < 160; i++) asm volatile("mov.b32 %0, %1;" : "=f"(s[i]) : "f"((i >> 5) < 4 - 2 * r - hf ? NEG : 0.f));
                    }
                    WG_FENCE();
                    wgmma_sk_160<DQ, DK>(s, qd, kd, r < 2);
                    wgmma_sk_160<DQ, DK>(s, qd + 16, kd + 16, 1);
                    WG_COMMIT();
                    wgmma_sk_160<DQ, DK>(s + 80, qd, kd + 20 * 56, r < 2);
                    wgmma_sk_160<DQ, DK>(s + 80, qd + 16, kd + 20 * 56 + 16, 1);
                    WG_COMMIT();
                }
                const bool c0 = 2 * q > lr, c1 = 2 * q + 1 > lr;
                int i0 = 0x80000000, i1 = 0x80000000, i2 = 0x80000000, i3 = 0x80000000;
#pragma unroll
                for (int hh = 0; hh < 2; hh++) {
                    if (hh == 0) WG_WAIT(1); else WG_WAIT(0);
                    reg_fence<80>(s + 80 * hh);
#pragma unroll
                    for (int pp = 0; pp < 4; pp++) {
                        const bool me = pp == wi;
                        float* e = s + 8 * (pp + 16 * hh);
                        if (me && c0 == hh) { e[0] = NEG; e[6] = NEG; }
                        if (me && c1 == hh) { e[1] = NEG; e[7] = NEG; }
                        if (me) { e[2 + 2 * hh] = NEG; e[3 + 2 * hh] = NEG; }
                    }
                    if (hh) {
#pragma unroll
                        for (int i = 0; i < 24; i++) s[i] = (i >> 3) < wi ? s[136 + i] : s[i];
                    }
#pragma unroll
                    for (int pp = 0; pp < 17; pp++) {
                        if ((pp >= 3 && pp < 10) == (hh == 0)) {
                            const float* e = s + 8 * pp;
                            i0 = __vimax3_s32(i0, __float_as_int(e[0]), __float_as_int(e[1])); i1 = __vimax3_s32(i1, __float_as_int(e[2]), __float_as_int(e[3]));
                            i2 = __vimax3_s32(i2, __float_as_int(e[4]), __float_as_int(e[5])); i3 = __vimax3_s32(i3, __float_as_int(e[6]), __float_as_int(e[7]));
                        }
                    }
                }
                i0 = max(i0, i2); i1 = max(i1, i3);
                i0 = max(i0, __shfl_xor_sync(~0u, i0, 1)); i1 = max(i1, __shfl_xor_sync(~0u, i1, 1));
                i0 = max(i0, __shfl_xor_sync(~0u, i0, 2)); i1 = max(i1, __shfl_xor_sync(~0u, i1, 2));
                if (__any_sync(~0u, (i0 | i1) < 0)) {
                    uint32_t u0 = ~0u, u1 = ~0u, u2 = ~0u, u3 = ~0u;
#pragma unroll
                    for (int pp = 0; pp < 17; pp++) {
                        const float* e = s + 8 * pp;
                        u0 = __vimin3_u32(u0, __float_as_uint(e[0]), __float_as_uint(e[1])); u1 = __vimin3_u32(u1, __float_as_uint(e[2]), __float_as_uint(e[3]));
                        u2 = __vimin3_u32(u2, __float_as_uint(e[4]), __float_as_uint(e[5])); u3 = __vimin3_u32(u3, __float_as_uint(e[6]), __float_as_uint(e[7]));
                    }
                    u0 = min(u0, u2); u1 = min(u1, u3);
                    u0 = min(u0, __shfl_xor_sync(~0u, u0, 1)); u1 = min(u1, __shfl_xor_sync(~0u, u1, 1));
                    u0 = min(u0, __shfl_xor_sync(~0u, u0, 2)); u1 = min(u1, __shfl_xor_sync(~0u, u1, 2));
                    if (i0 < 0) i0 = u0;
                    if (i1 < 0) i1 = u1;
                }
                const float ma = __int_as_float(i0), mb = __int_as_float(i1);
                const float na = -ma * CS, nb = -mb * CS;
                PROFC(8 + 3 * hf);
                {
                    float o[16] = {}, rs[4] = {};
                    const uint32_t va = sb + OFF_Y + Y_VR + (8 * hf + ((lane >> 3) & 1)) * 896 + (3 * w + (lane >> 4)) * 128 + (lane & 7) * 16;
                    constexpr uint32_t OWN = Y_VOWN - 32 * 896;
                    auto pv = [&](int pp) {
                        uint32_t B[8];
                        const uint32_t v = va + pp * 1792 + (pp < 3 ? (pp < wi ? 17 * 1792 + OWN : 0) : pp == 16 ? OWN : pp >= 12 ? hf * OWN : 0);
                        ldsm4t(v, B); ldsm4t(v + 256, B + 4);
                        float e[8];
#pragma unroll
                        for (int i = 0; i < 8; i++) e[i] = ex2(fmaf(s[8 * pp + i], CS, (i & 2) ? nb : na));
                        const uint32_t p0 = pack2(e[0], e[1]), p1 = pack2(e[2], e[3]), p2 = pack2(e[4], e[5]), p3 = pack2(e[6], e[7]);
                        mma16816(rs, p0, p1, p2, p3, 0x3F803F80u, 0x3F803F80u);
#pragma unroll
                        for (int g = 0; g < 4; g++) mma16816(o + 4 * g, p0, p1, p2, p3, B[2 * g], B[2 * g + 1]);
                    };
                    if (r >= 2) {
                        pv(16);
                        WAIT(B_VRFULL, 0);
#pragma unroll
                        for (int pp = 0; pp < 16; pp++) pv(pp);
                    } else {
                        WAIT(B_VRFULL, 0);
                        pv(0); pv(1); pv(2); pv(16);
#pragma unroll
                        for (int p4 = 1; p4 < 4; p4++)
                            if (p4 >= 4 - 2 * r - hf) { pv(4 * p4); pv(4 * p4 + 1); pv(4 * p4 + 2); pv(4 * p4 + 3); }
                    }
                    PROFC(9 + 3 * hf);
                    const float ia = rcp(rs[0]), ib = rcp(rs[2]);
                    uint32_t* og = act + RB_O + hf * 14336 + (7 * j + 3 * w) * 256 + wi * 64 + lane;
#pragma unroll
                    for (int g = 0; g < 4; g++) {
                        if ((g == 3 - 3 * w) ? ((q >> 1) == w) : true) {
                            og[g * 256] = pack2(o[4 * g] * ia, o[4 * g + 1] * ia);
                            og[g * 256 + 32] = pack2(o[4 * g + 2] * ib, o[4 * g + 3] * ib);
                        }
                    }
                    warp_arrive(BAR(B_PUB + 2 + hf));
                    PROFC(10 + 3 * hf);
                }
            }
        }
        uint32_t x1p[14], xr[16];
        COORDS
        {
            const uint32_t xa = sb + OFF_Y + (w ? Y_Q : Y_K) + (16 * wi + ((lane >> 3) & 1) * 8 + (lane & 7)) * 112 + (lane >> 4) * 16;
            WAIT(B_KRFULL, 1);
#pragma unroll
            for (int i = 0; i < 4; i++) ldsm4(xa + 32 * i, xr + 4 * i);
            warp_arrive(BAR(B_XFREE));
        }
        constexpr uint64_t DT = dconst(1024, 128, 0);
        const uint32_t epoch = lds1(sb + M_EPOCH);
        const int tile = opaque((epoch & 1) * 2 + w);
        {
            float ac[28];
            const uint32_t ad = mkdesc(sb + (w ? OFF_Y + HALF : OFF_X), DT), bd = mkdesc(sb + OFF_X + HALF, DB128) + kh;
            WAIT(B_WOFULL, 0);
            WAIT(B_MOD1, 1);
            WAIT(B_GFULL + w, 0);
            PROFC(28);
            reg_def<28>(ac);
#pragma unroll 1
            for (int u = 0; u < 4; u++) {
                if (u == 2) WAIT(B_XFULL + 2 + w, 1);
                WG_FENCE();
#pragma unroll
                for (int i = 0; i < 7; i++) wgmma_ss_56<DT, DB128>(ac, ad + (7 * u + i) * 128, bd + (7 * u + i) * 128, (u | i) != 0);
            }
            WG_COMMIT();
            WG_WAIT(0);
            reg_fence<28>(ac);
            PROFC(14);
            __syncwarp();
            if (lane < 4) mbar_arrive(BAR(B_EMPTY + 3 + lane));
            if (lane < 3 && w == 0) mbar_arrive(BAR(B_EMPTY + lane));
            float ds[4] = {}, da[4] = {}, db[4] = {};
            uint32_t* xo = act + RB_X1 + tile * 14336 + 7 * j * 256 + wi * 64 + lane;
#pragma unroll
            for (int g = 0; g < 7; g++) {
                const float2 ga = *(const float2*)(smem + M_G + (8 * g + 2 * q) * 4);
                x1p[2 * g] = pack2(fmaf(ga.x, ac[4 * g], bf_lo(xr[2 * g])), fmaf(ga.y, ac[4 * g + 1], bf_hi(xr[2 * g])));
                x1p[2 * g + 1] = pack2(fmaf(ga.x, ac[4 * g + 2], bf_lo(xr[2 * g + 1])), fmaf(ga.y, ac[4 * g + 3], bf_hi(xr[2 * g + 1])));
                st_relaxed(xo + g * 256, nz(x1p[2 * g])); st_relaxed(xo + g * 256 + 32, nz(x1p[2 * g + 1]));
                mma1688(ds, x1p[2 * g], x1p[2 * g + 1], 0x3F803F80u);
                mma1688(da, x1p[2 * g], x1p[2 * g + 1], x1p[2 * g]);
                mma1688(db, x1p[2 * g], x1p[2 * g + 1], x1p[2 * g + 1]);
            }
            if (lane < 8) st_relaxed(g_flag + (8 * r + lane) * 192 + 128 + 32 * w + 4 * j + wi, epoch + 1);
            const int src = (lane & ~3) | (lr >> 1);
            const float qa = __shfl_sync(~0u, (lr & 1) ? da[1] : da[0], src), qb = __shfl_sync(~0u, (lr & 1) ? db[3] : db[2], src);
            const float kk = (q & 1) ? ((q & 2) ? qb : qa) : ((q & 2) ? ds[2] : ds[0]);
            st_relaxed(act + RB_ST + ((tile * 8 + j) * 64 + 16 * wi + lr + 4 * (q & 2)) * 2 + (q & 1), nz(__float_as_uint(kk)));
        }
        PROFC(15);
        uint32_t h2a[32], h2b[24];
        {
            const int fa = pass_f(fs, 0), fb = pass_f(fs, 1), fc = pass_f(fs, 2);
            uint32_t* h2g = act + RB_H2 + (8 * w + 2 * wi) * 32 + lane;
            const uint32_t a0 = mkdesc(sb + OFF_Y + w * HALF, DT);
            {
                LnRow ca, cb;
                {
                    const uint32_t* sg = act + RB_ST + ((tile * 8 + 2 * q) * 64 + 16 * wi + lr) * 2;
                    uint2 u[4];
                    WAIT(B_FULLV + w, 1);
                    PROFC(16);
                    do {
#pragma unroll
                        for (int i = 0; i < 4; i++) u[i] = ld_relaxed2(sg + (i >> 1) * 128 + (i & 1) * 16);
                    } while (__any_sync(~0u, min(min(min(u[0].x, u[0].y), min(u[1].x, u[1].y)), min(min(u[2].x, u[2].y), min(u[3].x, u[3].y))) == 0u));
                    float v[4] = {__uint_as_float(u[0].x) + __uint_as_float(u[2].x), __uint_as_float(u[0].y) + __uint_as_float(u[2].y),
                                  __uint_as_float(u[1].x) + __uint_as_float(u[3].x), __uint_as_float(u[1].y) + __uint_as_float(u[3].y)};
#pragma unroll
                    for (int i = 0; i < 4; i++) { v[i] += __shfl_xor_sync(~0u, v[i], 1); v[i] += __shfl_xor_sync(~0u, v[i], 2); }
                    ca = ln_coeffs(v[0] * (1.f / DM), v[1] * (1.f / DM));
                    cb = ln_coeffs(v[2] * (1.f / DM), v[3] * (1.f / DM));
                }
                const uint32_t ha = sb + OFF_Y + w * HALF + (lane >> 4) * 1024 + (2 * wi + ((lane >> 3) & 1)) * 128 + (lane & 7) * 16;
                const uint32_t sta = sb + M_ST + q * 16;
                const uint32_t* xg = act + RB_X1 + tile * 14336 + (lane >> 4) * 256 + wi * 64 + (lane & 15) * 4;
                uint32_t x[8];
                const uint32_t xs = sb + OFF_Y + w * HALF + (lane >> 4) * 1024 + wi * 256 + (lane & 15) * 16;
                uint4 st[2];
                auto load = [&](int s) {
                    if (s == 4) mbar_wait_c(BAR(B_XFULL + 4 + w), 1);
                    ldsm4(ha + s * 4096, x); ldsm4(ha + s * 4096 + 2048, x + 4);
                    st[0] = lds4(sta + s * 128); st[1] = lds4(sta + s * 128 + 64);
                };
                auto prep = [&](int s, uint32_t* f) {
                    if (__any_sync(~0u, min(min(min(x[0], x[1]), min(x[2], x[3])), min(min(x[4], x[5]), min(x[6], x[7]))) == 0u)) {
                        WG_WAIT(0);
                        x1_fix(xg, xs, s);
                        ldsm4(ha + s * 4096, x); ldsm4(ha + s * 4096 + 2048, x + 4);
                    }
#pragma unroll
                    for (int i = 0; i < 2; i++) {
                        f[4 * i] = ln_mod(ln_norm(x[4 * i], ca), st[i].x, st[i].y); f[4 * i + 1] = ln_mod(ln_norm(x[4 * i + 1], cb), st[i].x, st[i].y);
                        f[4 * i + 2] = ln_mod(ln_norm(x[4 * i + 2], ca), st[i].z, st[i].w); f[4 * i + 3] = ln_mod(ln_norm(x[4 * i + 3], cb), st[i].z, st[i].w);
                    }
                    if (s < 13) load(s + 1);
                    stsm4(ha + s * 4096, f[0], f[1], f[2], f[3]); stsm4(ha + s * 4096 + 2048, f[4], f[5], f[6], f[7]);
                };
                float ac[128];
                uint32_t fr[3][8];
                uint64_t bd = (DB128 & ~0xFFFFFFFFull) | mkdesc(sb, DB128);
                reg_def<128>(ac);
                WAIT(B_GFULL + 2 + w, 0);
                load(0);
                prep(0, fr[0]);
                PROFC(17);
#pragma unroll
                for (int s = 0; s < 14; s++) {
                    const uint32_t* f = fr[s % 3];
                    WAIT(B_FULL + g1_slot(s), s >= 7);
                    WG_FENCE();
                    wgmma_rl_256(ac, f[0], f[1], f[2], f[3], bd, s != 0);
                    wgmma_rl_256(ac, f[4], f[5], f[6], f[7], bd + 128, 1);
                    bd += s == 6 ? p.zero - 6 * 1024ull : 1024;
                    WG_COMMIT();
                    if (s < 13) prep(s + 1, fr[(s + 1) % 3]);
                    if (s > 0) { WG_WAIT(1); warp_arrive(BAR(B_EMPTY + g1_slot(s - 1))); }
                }
                fence_async_smem();
                PROFC(18);
                WG_WAIT(0);
                reg_fence<128>(ac);
                warp_arrive(BAR(B_EMPTY + 6));
#pragma unroll
                for (int g = 0; g < 16; g++) {
                    h2a[2 * g] = hmul2(pack2_relu(ac[4 * g], ac[4 * g + 1]), pack2(ac[64 + 4 * g], ac[64 + 4 * g + 1]));
                    h2a[2 * g + 1] = hmul2(pack2_relu(ac[4 * g + 2], ac[4 * g + 3]), pack2(ac[64 + 4 * g + 2], ac[64 + 4 * g + 3]));
                }
                bar_sync(1 + w, 128);
            }
            PROFC(19);
            {
                float ac[64];
                reg_def<64>(ac);
                const uint32_t bx = mkdesc(sb, dconst(8192, 1024, 1));
#pragma unroll 1
                for (int s = 0; s < 7; s++) {
                    WAIT(B_FULL + s, 0);
                    const uint32_t ad = a0 + s * 512, bd = bx + (slot_off(s) >> 4);
                    WG_FENCE();
#pragma unroll
                    for (int k = 0; k < 4; k++) wgmma_ss_128<DT, DB128>(ac, ad + k * 128, bd + k * 128, (s | k) != 0);
                    WG_COMMIT();
                    if (s == 0) {
#pragma unroll
                        for (int g = 0; g < 16; g++) { h2g[(fa / 8 + g) * 512] = h2a[2 * g]; h2g[(fa / 8 + g) * 512 + 32] = h2a[2 * g + 1]; }
                        warp_arrive(BAR(B_PUB + 6));
                    }
                    if (s > 0) { WG_WAIT(1); warp_arrive(BAR(B_EMPTY + s - 1)); }
                }
                WG_WAIT(0);
                reg_fence<64>(ac);
                warp_arrive(BAR(B_EMPTY + 6));
#pragma unroll
                for (int g = 0; g < 8; g++) {
                    h2b[2 * g] = hmul2(pack2_relu(ac[4 * g], ac[4 * g + 1]), pack2(ac[32 + 4 * g], ac[32 + 4 * g + 1]));
                    h2b[2 * g + 1] = hmul2(pack2_relu(ac[4 * g + 2], ac[4 * g + 3]), pack2(ac[32 + 4 * g + 2], ac[32 + 4 * g + 3]));
                }
            }
            PROFC(27);
            {
                float ac[32];
                reg_def<32>(ac);
                const uint32_t bx = mkdesc(sb, dconst(4096, 512, 2));
#pragma unroll 1
                for (int s = 0; s < 7; s++) {
                    WAIT(B_FULL + (s >> 1), 1);
                    const uint32_t ad = a0 + s * 512, bd = bx + s * 512;
                    WG_FENCE();
#pragma unroll
                    for (int k = 0; k < 4; k++) wgmma_ss_64<DT, dconst(4096, 512, 2)>(ac, ad + k * 128, bd + k * 64, (s | k) != 0);
                    WG_COMMIT();
                    if (s == 0) {
#pragma unroll
                        for (int g = 0; g < 8; g++) { h2g[(fb / 8 + g) * 512] = h2b[2 * g]; h2g[(fb / 8 + g) * 512 + 32] = h2b[2 * g + 1]; }
                        warp_arrive(BAR(B_PUB + 7));
                    }
                    if (s > 0 && !(s & 1)) {
                        WG_WAIT(1);
                        __syncwarp();
                        if (lane < 3) mbar_arrive(BAR(B_EMPTY + (s >> 1) - 1 + (lane ? 4 + 3 * lane : 0)));
                    }
                }
                WG_WAIT(0);
                reg_fence<32>(ac);
                PROFC(20);
#pragma unroll
                for (int g = 0; g < 4; g++) {
                    h2b[16 + 2 * g] = hmul2(pack2_relu(ac[4 * g], ac[4 * g + 1]), pack2(ac[16 + 4 * g], ac[16 + 4 * g + 1]));
                    h2b[16 + 2 * g + 1] = hmul2(pack2_relu(ac[4 * g + 2], ac[4 * g + 3]), pack2(ac[16 + 4 * g + 2], ac[16 + 4 * g + 3]));
                    h2g[(fc / 8 + g) * 512] = h2b[16 + 2 * g]; h2g[(fc / 8 + g) * 512 + 32] = h2b[16 + 2 * g + 1];
                }
                warp_arrive(BAR(B_PUB + 8));
                asm volatile("barrier.cluster.wait.aligned;" ::: "memory");
                if (lane == 0) {
                    uint32_t rb;
                    asm volatile("mapa.shared::cluster.u32 %0, %1, %2;" : "=r"(rb) : "r"(BAR(B_PEER)), "r"(kh ^ 1));
                    asm volatile("mbarrier.arrive.relaxed.cluster.shared::cluster.b64 _, [%0];" ::"r"(rb) : "memory");
                }
            }
        }
        PROFC(21);
        {
            float ac[56];
            reg_def<56>(ac);
            constexpr uint64_t DAN = dconst(2048, 128, 0);
            constexpr uint64_t DW = dconst(128, 512, 0);
            const uint32_t bx = mkdesc(sb, DW);
#pragma unroll
            for (int e = 3; e < 7; e++) {
                if (e > 3) WAIT(B_FULL + e, 1);
                const uint64_t bd = ((DW & ~0xFFFFFFFFull) | bx) + (slot_off(e) >> 4);
                const uint32_t* hh = e == 3 ? h2b + 8 : e < 6 ? h2a + 16 * (e - 4) : h2b;
                WG_FENCE();
#pragma unroll
                for (int k = e == 3 ? 2 : 0; k < 4; k++) wgmma_rl_112(ac, hh[4 * k], hh[4 * k + 1], hh[4 * k + 2], hh[4 * k + 3], bd + (k >> 1) * 512 + (k & 1) * 16, e > 3 || k > 2);
                WG_COMMIT();
                if (e > 3) { WG_WAIT(1); warp_arrive(BAR(B_EMPTY + e - 1)); }
            }
            PROFC(22);
            const uint32_t ax = mkdesc(sb + 8192 + w * 1024, DAN);
            uint32_t eb_ = BAR(B_EMPTY + 6);
            uint64_t ord = RING_ORDER;
#pragma unroll 1
            for (int e = 0; e < 21; e++) {
                const uint32_t sl = ord & 15, so = slot_off(sl) >> 4;
                ord = e == 12 ? RING_ORDER : ord >> 4;
                mbar_wait_c(BAR(B_FULL + sl), e >= 13);
                WG_FENCE();
                wgmma_ss_112<DAN, DW>(ac, ax + so, bx + so, 1);
                wgmma_ss_112<DAN, DW>(ac, ax + so + 256, bx + so + 16, 1);
                WG_COMMIT();
                WG_WAIT(1);
                warp_arrive(eb_);
                eb_ = BAR(B_EMPTY + sl);
            }
            mbar_wait_cluster(BAR(B_PEER), 0);
            WG_WAIT(0);
            reg_fence<56>(ac);
            PROFC(24);
            uint32_t rdst, rbar;
            asm volatile("mapa.shared::cluster.u32 %0, %1, %2;" : "=r"(rdst) : "r"(sb + OFF_Y + Y_XCH + w * HALF + t * 16), "r"(kh ^ 1));
            asm volatile("mapa.shared::cluster.u32 %0, %1, %2;" : "=r"(rbar) : "r"(BAR(B_XCH + w)), "r"(kh ^ 1));
#pragma unroll
            for (int g = 0; g < 3; g++)
                asm volatile("st.async.shared::cluster.mbarrier::complete_tx::bytes.v4.b32 [%0], {%1,%2,%3,%4}, [%5];" ::"r"(rdst + g * 2048),
                             "r"(pack2(ac[28 + 8 * g], ac[29 + 8 * g])), "r"(pack2(ac[30 + 8 * g], ac[31 + 8 * g])), "r"(pack2(ac[32 + 8 * g], ac[33 + 8 * g])),
                             "r"(pack2(ac[34 + 8 * g], ac[35 + 8 * g])), "r"(rbar) : "memory");
            asm volatile("st.async.shared::cluster.mbarrier::complete_tx::bytes.v2.b32 [%0], {%1,%2}, [%3];" ::"r"(rdst + 6144 - t * 8),
                         "r"(pack2(ac[52], ac[53])), "r"(pack2(ac[54], ac[55])), "r"(rbar) : "memory");
            mbar_wait_cluster(BAR(B_XCH + w), 0);
            PROFC(25);
            uint32_t op[14], rv[14];
#pragma unroll
            for (int g = 0; g < 3; g++) *(uint4*)(rv + 4 * g) = *(const uint4*)(smem + OFF_Y + Y_XCH + w * HALF + t * 16 + g * 2048);
            *(uint2*)(rv + 12) = *(const uint2*)(smem + OFF_Y + Y_XCH + w * HALF + 6144 + t * 8);
#pragma unroll
            for (int i = 0; i < 14; i++) {
                const float2 gb = *(const float2*)(smem + M_G + 224 + (8 * (i >> 1) + 2 * q) * 4);
                op[i] = pack2(fmaf(gb.x, ac[2 * i] + bf_lo(rv[i]), bf_lo(x1p[i])), fmaf(gb.y, ac[2 * i + 1] + bf_hi(rv[i]), bf_hi(x1p[i])));
            }
            WAIT(B_EMPTY + 4, 1);
            const uint32_t oc = sb + OUT_STAGE + warp * 1792;
            const uint32_t oa = oc + (((lane >> 3) & 1) * 8 + (lane & 7)) * 112 + (lane >> 4) * 16;
            stsm4(oa, op[0], op[1], op[2], op[3]); stsm4(oa + 32, op[4], op[5], op[6], op[7]); stsm4(oa + 64, op[8], op[9], op[10], op[11]);
            asm volatile("stmatrix.sync.aligned.m8n8.x2.shared.b16 [%0], {%1,%2};" ::"r"(oa + 96), "r"(op[12]), "r"(op[13]));
            fence_async_smem();
            __syncwarp();
            asm volatile("{\n.reg .pred p;\nelect.sync _|p, 0xffffffff;\n@p cp.async.bulk.tensor.3d.global.shared::cta.bulk_group [%0, {%2, %3, %4}], [%1];\n"
                         "cp.async.bulk.commit_group;\ncp.async.bulk.wait_group.read 0;\n}" ::"l"(&p.om), "r"(oc), "r"(56 * j), "r"(128 * r + 64 * w + 16 * wi), "r"(0) : "memory");
        }
        PROFC(26);
        bar_sync(1 + w, 128);
        if (wi == 0) warp_arrive(BAR(B_DONE));
        return;
    }
    helper_late(p, r, j, warp PROF_ARGS);
}

#undef act
typedef CUresult (*EncodeFn)(CUtensorMap*, CUtensorMapDataType, cuuint32_t, void*, const cuuint64_t*, const cuuint64_t*, const cuuint32_t*,
                             const cuuint32_t*, CUtensorMapInterleave, CUtensorMapSwizzle, CUtensorMapL2promotion, CUtensorMapFloatOOBfill);

static void make_map(EncodeFn fn, CUtensorMap* m, const void* ptr, uint64_t d0, uint64_t d1, uint64_t d2, uint64_t s1, uint64_t s2,
                     uint32_t b0, uint32_t b1, uint32_t b2, CUtensorMapSwizzle sw) {
    cuuint64_t dims[3] = {d0, d1, d2}, strides[2] = {s1, s2};
    cuuint32_t box[3] = {b0, b1, b2}, es[3] = {1, 1, 1};
    CUresult rc = fn(m, CU_TENSOR_MAP_DATA_TYPE_BFLOAT16, 3, (void*)ptr, dims, strides, box, es, CU_TENSOR_MAP_INTERLEAVE_NONE, sw,
                     CU_TENSOR_MAP_L2_PROMOTION_L2_128B, CU_TENSOR_MAP_FLOAT_OOB_FILL_NONE);
    (void)rc;
}

extern "C" void kernel_launch(void* const* d_in, const int* in_sizes, int n_in, void* d_out, int out_size) {
    (void)in_sizes; (void)n_in; (void)out_size;
    static EncodeFn fn = nullptr;
    static uint32_t* act_base = nullptr;
    if (!fn) {
        cudaDriverEntryPointQueryResult st;
        cudaGetDriverEntryPoint("cuTensorMapEncodeTiled", (void**)&fn, cudaEnableDefault, &st);
        void* a = nullptr;
        cudaGetSymbolAddress(&a, g_act);
        act_base = (uint32_t*)(((uintptr_t)a + 0xFFFFF) & ~(uintptr_t)0xFFFFF);
        cudaFuncSetAttribute(fused_block_kernel, cudaFuncAttributeMaxDynamicSharedMemorySize, SMEM_BYTES);
    }
    Params p;
    p.x = (const bf16*)d_in[0];
    const bf16* wqkv = (const bf16*)d_in[1];
    p.wqkv = wqkv;
    p.wop = (const bf16*)d_in[2];
    p.wg = (const bf16*)d_in[4];
    p.wu = (const bf16*)d_in[5];
    p.wd = (const bf16*)d_in[6];
    p.c = (const bf16*)d_in[7];
    p.wmod = (const bf16*)d_in[8];
    p.out = (bf16*)d_out;
    p.zero = 0;
    p.actb = act_base;
    make_map(fn, &p.wm, p.wmod, 2688, 448, 1, 5376, 5376 * 448, 16, 224, 1, CU_TENSOR_MAP_SWIZZLE_NONE);
    make_map(fn, &p.wm2, p.wmod, 2688, 448, 1, 5376, 5376 * 448, 32, 224, 1, CU_TENSOR_MAP_SWIZZLE_NONE);
    make_map(fn, &p.om, p.out, 448, 2048, 1, 896, 896 * 2048, 56, 16, 1, CU_TENSOR_MAP_SWIZZLE_NONE);
    make_map(fn, &p.xr, p.x, 448, 2048, 1, 896, 896 * 2048, 56, 64, 1, CU_TENSOR_MAP_SWIZZLE_NONE);
    make_map(fn, &p.xm, p.x, 448, 2048, 1, 896, 896 * 2048, 64, 128, 1, CU_TENSOR_MAP_SWIZZLE_128B);
    make_map(fn, &p.qkv, wqkv, 1344, 448, 1, 2688, 2688 * 448, 64, 224, 1, CU_TENSOR_MAP_SWIZZLE_128B);
    make_map(fn, &p.wo, p.wop, 448, 448, 1, 896, 896 * 448, 64, 224, 1, CU_TENSOR_MAP_SWIZZLE_128B);
    make_map(fn, &p.ga, p.wg, 64, 448, 28, 3584, 128, 64, 32, 2, CU_TENSOR_MAP_SWIZZLE_128B);
    make_map(fn, &p.ua, p.wu, 64, 448, 28, 3584, 128, 64, 32, 2, CU_TENSOR_MAP_SWIZZLE_128B);
    make_map(fn, &p.gb, p.wg, 64, 448, 28, 3584, 128, 64, 64, 1, CU_TENSOR_MAP_SWIZZLE_128B);
    make_map(fn, &p.ub, p.wu, 64, 448, 28, 3584, 128, 64, 64, 1, CU_TENSOR_MAP_SWIZZLE_128B);
    make_map(fn, &p.gc, p.wg, 32, 448, 56, 3584, 64, 32, 64, 1, CU_TENSOR_MAP_SWIZZLE_64B);
    make_map(fn, &p.uc, p.wu, 32, 448, 56, 3584, 64, 32, 64, 1, CU_TENSOR_MAP_SWIZZLE_64B);
    make_map(fn, &p.dn, p.wd, 8, 1792, 56, 896, 16, 8, 32, 7, CU_TENSOR_MAP_SWIZZLE_NONE);
    fused_block_kernel<<<NCTA, 384, SMEM_BYTES>>>(p);
}
```
